```python
import torch

def _softmax(x, axis=-1):
    return torch.softmax(x, dim=axis)
def _gelu(x):
    return torch.nn.functional.gelu(x, approximate="tanh")
def _silu(x):
    return torch.nn.functional.silu(x)
def _sigmoid(x):
    return torch.sigmoid(x)
def _layernorm(x, axis=-1, eps=1e-5):
    m = x.mean(dim=axis, keepdim=True)
    v = x.var(dim=axis, keepdim=True, unbiased=False)
    return (x - m) / torch.sqrt(v + eps)
def _scatter_add(tgt, idx, src, axis=0):
    return tgt.clone().index_add_(axis, idx, src)
def _segment_sum(src, seg, n):
    out = torch.zeros((n,) + src.shape[1:], dtype=src.dtype)
    return out.index_add_(0, seg, src)
def _pad(x, pw):
    flat = tuple(v for pair in reversed(pw) for v in pair)
    return torch.nn.functional.pad(x, flat)

kernel_name = 'concat_heads__ssm_conv_h3__sliding_local_dilated__prompt'

def setup_inputs():

    _w = (lambda a: (lambda t: t.to(torch.bfloat16) if t.is_floating_point() else t)(torch.as_tensor(a)))
    def _A_setup():
        B, S, D = 1, 2048, 1024
        ks = 4
        return {
            "q": _w((lambda *s: torch.randn(*s, dtype=torch.bfloat16) * 0.05)(B, S, D)),
            "k": _w((lambda *s: torch.randn(*s, dtype=torch.bfloat16) * 1.6)(B, S, D)),
            "v": _w((lambda *s: torch.randn(*s, dtype=torch.bfloat16) * 0.8)(B, S, D)),
            "shift_k": _w((lambda *s: torch.randn(*s, dtype=torch.bfloat16) * 1.6)(D, ks) * 0.5),
            "ssm_k": _w((lambda *s: torch.randn(*s, dtype=torch.bfloat16) * 1.6)(D, S) * (1.0 / S ** 0.5)),
            "ssm_D": _w((lambda *s: torch.randn(*s, dtype=torch.bfloat16) * 0.8)(D)),
        }
    _A_in = _A_setup()

    def _B_setup():
        B, S, D = 1, 2048, 1024
        return {
            "x": _w((lambda *s: torch.randn(*s, dtype=torch.bfloat16) * 0.2)(B, S, D)),
            "wqkv": _w((lambda *s: torch.randn(*s, dtype=torch.bfloat16) * 0.2)(D, 3 * D)),
            "wo": _w((lambda *s: torch.randn(*s, dtype=torch.bfloat16) * 0.05)(D, D)),
        }
    _B_in = _B_setup()

    return {
        "A_q": _A_in["q"],
        "A_k": _A_in["k"],
        "A_v": _A_in["v"],
        "A_shift_k": _A_in["shift_k"],
        "A_ssm_k": _A_in["ssm_k"],
        "A_ssm_D": _A_in["ssm_D"],
        "B_x": _B_in["x"],
        "B_wqkv": _B_in["wqkv"],
        "B_wo": _B_in["wo"],
    }

def reference(A_q, A_k, A_v, A_shift_k, A_ssm_k, A_ssm_D, B_x, B_wqkv, B_wo):
    def _A_ref(q, k, v, shift_k, ssm_k, ssm_D):
        B, S, D = q.shape
        ks = shift_k.shape[-1]
        k_pad = _pad(k, ((0, 0), (ks - 1, 0), (0, 0)))
        k_shift = torch.zeros_like(k)
        for t in range(ks):
            k_shift = k_shift + k_pad[:, t:t + S, :] * shift_k[:, ks - 1 - t][None, None, :]
        kv = k_shift * v
        L = 2 * S
        kv_pad = _pad(kv, ((0, 0), (0, S), (0, 0)))
        kf_pad = _pad(ssm_k, ((0, 0), (0, S)))
        kv_f = (lambda x, axes=(-2,-1): torch.fft.rfft2(x.float(), dim=axes))(kv_pad[:, None, :, :], axes=(1, 2))
        kf_f = (lambda x, axes=(-2,-1): torch.fft.rfft2(x.float(), dim=axes))(kf_pad[:, None, :], axes=(1, 2))
        kf_f = (lambda x, *d: x.permute(*d))(kf_f, 1, 2, 0)
        y_f = kv_f * kf_f[None, :, :, :]
        y = (lambda x, s, axes=(-2,-1): torch.fft.irfft2(x, s=s, dim=axes).to(torch.bfloat16))(y_f, (1, L), axes=(1, 2))[:, 0, :S, :]
        y = y + kv * ssm_D[None, None, :]
        return q * y

    def _B_ref(x, wqkv, wo):
        B, S, D = x.shape
        H = 32; Dh = D // H
        W, dil = 8, 2
        qkv = (lambda x, *d: x.permute(*d))((x @ wqkv).reshape(B, S, 3, H, Dh), 2, 0, 3, 1, 4)
        q, k, v = qkv[0], qkv[1], qkv[2]
        scale = Dh ** -0.5
        pos = torch.arange(S)
        off = torch.arange(W) * dil
        idx = pos[:, None] - off[None, :]
        mask = idx >= 0
        idx_c = torch.where(mask, idx, 0).reshape(-1)
        kg = k[:, :, idx_c, :].reshape(B, H, S, W, Dh)
        vg = v[:, :, idx_c, :].reshape(B, H, S, W, Dh)
        logits = torch.einsum("bhsd,bhswd->bhsw", q, kg) * scale
        logits = torch.where(mask[None, None, :, :], logits, -1e9)
        attn = _softmax(logits, axis=-1)
        o = torch.einsum("bhsw,bhswd->bhsd", attn, vg)
        return (lambda x, *d: x.permute(*d))(o, 0, 2, 1, 3).reshape(B, S, D) @ wo

    a = _A_ref(A_q, A_k, A_v, A_shift_k, A_ssm_k, A_ssm_D)
    b = _B_ref(B_x, B_wqkv, B_wo)
    return torch.concatenate([a, b], axis=-1)
```

```cpp
#include <cuda_runtime.h>
#include <cuda.h>
#include <cuda_bf16.h>
#include <stdint.h>

namespace {

constexpr int SEQ = 2048;
constexpr int DM = 1024;
constexpr int NCTA = 132;
constexpr int NTHREADS = 384;

constexpr int STG1A = 32768;
constexpr int NS1A = 3;
constexpr int STG1B = 12288;
constexpr int NS1B = 5;
constexpr int OFF_1B = NS1A * STG1A;
constexpr int STG2 = 32768;
constexpr int NS2 = 4;
constexpr int STGH = 73728;
constexpr int OFF_VP = 0;
constexpr int OFF_KH = 1 * STG2;
constexpr int OFF_OP = 2 * STG2;
constexpr int T_A4 = 0, T_TW = 16384, T_B2 = 24576, T_B3 = 28672, T_A1 = 30720, T_END = 34816;
constexpr int OFF_U = 163840;
constexpr int OFF_H = OFF_U + 32768;
constexpr int OFF_T = OFF_U - T_END;
constexpr int OFF_LAND = NS2 * STG2;
constexpr int OFF_BAR = OFF_H + 32768;
constexpr int OFF_SC = OFF_BAR + 512;
constexpr int OFF_L0 = OFF_BAR + 1024;
constexpr int SMEM_BYTES = OFF_L0 + 2048;
static_assert(OFF_T + T_A1 == OFF_1B + NS1B * STG1B && OFF_T >= OFF_1B + 2 * STG1B && OFF_LAND + 16384 <= OFF_T + T_B2, "layout");
static_assert(3 * STGH <= OFF_BAR && SMEM_BYTES <= 232448, "smem");

constexpr int BAR_FULLA = 0;
constexpr int BAR_EMPTYA = 3;
constexpr int BAR_FULLB = 6;
constexpr int BAR_EMPTYB = 11;
constexpr int BAR_FULL2 = 16;
constexpr int BAR_EMPTY2 = 20;
constexpr int BAR_T = 24;
constexpr int BAR_UH = 25;
constexpr int BAR_LFREE = 26;
constexpr int BAR_LAND = 27;
constexpr int BAR_U = 28;
constexpr int BAR_Q = 29;
constexpr int BAR_STG = 31;
constexpr int BAR_QF = 32;

constexpr int NB_G1DONE = 1;
constexpr int NB_OREADY = 2;
constexpr int NB_WG = 4;
constexpr int NB_HELP3 = 6;
constexpr int NB_FIRST = 7;

#define REG_MATH 224
#define REG_HELP 56
constexpr int SPIN_LIMIT = 1 << 20;

__device__ __align__(1024) __nv_bfloat16 g_o[SEQ * DM];
__device__ uint32_t g_flag_o[256];
__device__ uint32_t g_flag_h[4];
__device__ uint4 g_halo[128 * 128];
__device__ __align__(128) const uint32_t g_tab[T_END / 4] = {
0x3c003c00,0x3bf13bff,0,0xafd6a648,0x3c003c00,0x3b993bce,0,0xb505b303,0x3c003c00,0x3af63b50,0,0xb7e3b67c,
0x3c003c00,0x3a0f3a8a,0,0xb93ab89b,0x3bc33bfe,0x3b773bfa,0xb3c6aa48,0xb5c2acb5,0x3a6d3b3b,0x389b3a4f,0xb8c4b6d7,0xba8ab8ec,
0x381d395f,0x26483505,0xbaddb9ed,0xbbffbb99,0x30b23564,0xb848b444,0xbbeabb88,0xbac2bbb6,0x3b0e3bf6,0x3a8a3bf1,0xb78bae46,0xb89bafd6,
0x34a53913,0xa6483732,0xbba8ba2f,0xbbffbb25,0xb78bae46,0xbac2b7e3,0xbb0ebbf6,0xb848baf6,0xbba8ba2f,0xbb50bbfa,0xb4a5b913,0x367cacb5,
0x39ed3bea,0x393a3be2,0xb95fb0b2,0xba0fb179,0xb56433c6,0xb8ec2648,0xbb88bbc3,0xba4fbbff,0xbbfeba6d,0xbb25bbce,0xaa48b8c4,0x3732b303,
0xb6d7badd,0x3444b67c,0x3b3b381d,0x3bb63b50,0x38723bd9,0x37323bce,0xbaa7b23e,0xbb25b303,0xbaa7b23e,0xbbb6b67c,0xb872bbd9,0xb444bb50,
0xb872bbd9,0xacb5ba8a,0x3aa7323e,0x3bfa389b,0x3aa7323e,0x3bf139cb,0x38723bd9,0xafd63984,0x35643bc3,0x33033bb6,0xbb88b3c6,0xbbceb444,
0xbbfeb8c4,0xbb77ba0f,0x2a48ba6d,0x35c2b93a,0x36d7b81d,0x3a8aafd6,0x3b3b3add,0x389b3bf1,0x395f3bea,0x26483b25,0xb9ed30b2,0xbbffb732,
0x2e463ba8,0xa6483b99,0xbbf6b4a5,0xbbffb505,0xba2fbb0e,0xb848bbb6,0x3913b78b,0x3ac2b444,0x3bf634a5,0x3b50393a,0x2e463ba8,0xb67c3a0f,
0xb913378b,0xbbe2afd6,0xba2fbb0e,0xb179bbf1,0xb0b23b88,0xb4443b77,0xbbeab564,0xbbb6b5c2,0xb3c6bbfe,0x2cb5bbe2,0x3bc3aa48,0x3bfa3179,
0x38c43b3b,0x2fd63bff,0xba6d36d7,0xbbf12648,0xbaddb95f,0xb505bbce,0x381db9ed,0x3b99b303,0xb61f3b64,0xb7e33b50,0xbb64b61f,0xbaf6b67c,
0x361fbb64,0x393aba8a,0x3b64361f,0x3a0f389b,0xb61f3b64,0xba4f3984,0xbb64b61f,0xb8ecb9cb,0x361fbb64,0x3b25b848,0x3b64361f,0x37323ac2,
0xb8c43b3b,0xb9843b25,0xba6db6d7,0xb9cbb732,0x3addb95f,0x3bceb7e3,0x381d39ed,0x33033af6,0xbbea3564,0xbb77acb5,0xb0b2bb88,0x35c2bbfa,
0x3bc32a48,0x389b38ec,0xb3c63bfe,0xba8a3a4f,0xba2f3b0e,0xbac23af6,0xb913b78b,0xb848b7e3,0x3bf6b4a5,0x3b50acb5,0xae463ba8,0xb67c3bfa,
0xb913b78b,0xb179ba4f,0x3a2fbb0e,0x3be2b8ec,0xae463ba8,0xb9cb3b99,0xbbf634a5,0xb984b505,0xbb3b3add,0xbb993ac2,0xb6d7b81d,0xb505b848,
0x39ed30b2,0x37e335c2,0xb95f3bea,0xbaf63b77,0x3564bbc3,0x3a0fbbe2,0x3b88b3c6,0x393a3179,0xbbfe38c4,0xba4f2648,0xaa48ba6d,0x38ecbbff,
0xbbd93aa7,0xbbfa3a8a,0xb23eb872,0xacb5b89b,0x323e3872,0xafd639cb,0xbbd93aa7,0xbbf13984,0x3bd9baa7,0x3b99b848,0x323e3872,0xb5053ac2,
0xb23eb872,0x37e3bb77,0x3bd9baa7,0x3af6b5c2,0xbbfe3a6d,0xbbe23a4f,0x2a48b8c4,0x3179b8ec,0xb6d73add,0xb9843b99,0xbb3b381d,0xb9cb3505,
0x395fb0b2,0x33033444,0xb9ed3bea,0xbbce3bb6,0x3b88bbc3,0x3b77b93a,0x356433c6,0xb5c23a0f,0xbba83a2f,0xbb503a0f,0x34a5b913,0x367cb93a,
0xbb0e3bf6,0xbbe23bf1,0xb78b2e46,0xb179afd6,0xb4a53913,0xb9cb3b25,0xbba83a2f,0xb9843732,0x378bae46,0xb30337e3,0xbb0e3bf6,0xbbce3af6,
0xbadd39ed,0xba4f39cb,0x381db95f,0x38ecb984,0xbbea3b88,0xbb253ac2,0x30b2b564,0x3732b848,0xbbc33bfe,0xbbb63b77,0xb3c62a48,0x3444b5c2,
0xba6d3b3b,0xbbfa3be2,0xb8c436d7,0x2cb5b179,0xb9a839a8,0xb8ec3984,0x39a8b9a8,0x3a4fb9cb,0xb9a839a8,0xb7323848,0x39a8b9a8,0x3b25bac2,
0xb9a839a8,0xb44435c2,0x39a8b9a8,0x3bb6bb77,0xb9a839a8,0xacb53179,0x39a8b9a8,0x3bfabbe2,0xb81d395f,0xb67c393a,0x3addb9ed,0x3b50ba0f,
0xb0b23564,0x31792fd6,0x3beabb88,0x3be2bbf1,0x33c6aa48,0x3984b732,0x3bc3bbfe,0x39cbbb25,0x38c4b6d7,0x3bcebaf6,0x3a6dbb3b,0x3303b7e3,
0xb4a53913,0xb17938ec,0x3ba8ba2f,0x3be2ba4f,0x378bae46,0x39cbb505,0x3b0ebbf6,0x3984bb99,0x3ba8ba2f,0x3bcebbb6,0x34a5b913,0xb303b444,
0x3b0ebbf6,0x35c2ba0f,0xb78b2e46,0xbb77393a,0xaa4838c4,0x2cb5389b,0x3bfeba6d,0x3bfaba8a,0x3b3bb81d,0x3bf1b984,0x36d7badd,0x2fd6b9cb,
0x39edbbea,0x3505bac2,0xb95f30b2,0xbb993848,0xb564b3c6,0xbaf635c2,0xbb883bc3,0xb7e33b77,0x323e3872,0x35053848,0x3bd9baa7,0x3b99bac2,
0x3bd9baa7,0x3af6bb77,0xb23eb872,0xb7e3b5c2,0xb23eb872,0xb93ab179,0xbbd93aa7,0xba0f3be2,0xbbd93aa7,0xb8ec3bff,0x323e3872,0x3a4fa648,
0x36d7381d,0x384837e3,0x3b3bbadd,0x3ac2baf6,0x395fbbea,0x367cbbfa,0xb9edb0b2,0xbb502cb5,0xbb8833c6,0xbbe238ec,0xb5643bc3,0x31793a4f,
0x2a483a6d,0x39843505,0x3bfeb8c4,0x39cbbb99,0x3913378b,0x39cb3732,0x3a2fbb0e,0x3984bb25,0x2e46bba8,0xb303baf6,0xbbf634a5,0xbbce37e3,
0xba2f3b0e,0xb5c23bfa,0x3913378b,0x3b772cb5,0x3bf6b4a5,0x3a8aba4f,0x2e46bba8,0xb89bb8ec,0x3a6d36d7,0x3af6367c,0x38c4bb3b,0x37e3bb50,
0xb81db9ed,0xba0fb89b,0xbadd395f,0xb93a3a8a,0x30b23b88,0x38ec39cb,0x3beab564,0x3a4fb984,0x33c6bbfe,0xb732bac2,0xbbc3aa48,0xbb253848,
0x3b64361f,0x3bb635c2,0x361fbb64,0x3444bb77,0xbb64b61f,0xbbfab179,0xb61f3b64,0xacb53be2,0x3b64361f,0x3bf1a648,0x361fbb64,0xafd6bbff,
0xbb64b61f,0xbb993303,0xb61f3b64,0x35053bce,0x3bea3564,0x3bff3505,0x30b2bb88,0x2648bb99,0xbbc32a48,0xbac23444,0x33c63bfe,0x38483bb6,
0x3a6db6d7,0x367cba0f,0xb8c4bb3b,0xbb50b93a,0xb81d39ed,0x31793bf1,0x3add395f,0x3be22fd6,0x3bf634a5,0x3bce3444,0xae46bba8,0xb303bbb6,
0xb913378b,0xb5c2393a,0x3a2f3b0e,0x3b773a0f,0xae46bba8,0xb89bbbf1,0xbbf6b4a5,0xba8a2fd6,0x3a2f3b0e,0x3bff3732,0x3913b78b,0xa648bb25,
0x3b8833c6,0x3b253303,0xb564bbc3,0xb732bbce,0xaa483a6d,0x34443b50,0x3bfe38c4,0x3bb6367c,0xbb3bbadd,0xbbfab89b,0xb6d7381d,0x2cb53a8a,
0x39edb0b2,0x2fd6b984,0xb95fbbea,0xbbf1b9cb,0x3aa7323e,0x3a0f3179,0xb872bbd9,0xb93abbe2,0x38723bd9,0x3a4f3bff,0x3aa7323e,0x38eca648,
0xbaa7b23e,0xb7323303,0x38723bd9,0x3b253bce,0xb872bbd9,0xbbb6bb50,0xbaa7b23e,0xb444367c,0x395f30b2,0x389b2fd6,0xb9edbbea,0xba8abbf1,
0x3b883bc3,0x3bff3b25,0x3564b3c6,0x2648b732,0x2a4838c4,0x38483af6,0x3bfe3a6d,0x3ac237e3,0xbb3bb81d,0xb67c2cb5,0x36d73add,0x3b503bfa,
0x378b2e46,0x35c22cb5,0xbb0ebbf6,0xbb77bbfa,0x3ba83a2f,0x3a8a38ec,0xb4a5b913,0xb89bba4f,0x3b0e3bf6,0x3bff3b99,0x378b2e46,0xa648b505,
0x34a53913,0x3ac23bb6,0x3ba83a2f,0x38483444,0x33c62a48,0x2fd62648,0xbbc3bbfe,0xbbf1bbff,0x38c436d7,0x35053303,0xba6dbb3b,0xbb99bbce,
0x3add39ed,0x37e3367c,0xb81db95f,0xbaf6bb50,0x3bea3b88,0x393a389b,0xb0b2b564,0xba0fba8a,0x3c003c00,0xbbf1bbff,0,0x2fd62648,
0x3c003c00,0xbb99bbce,0,0x35053303,0x3c003c00,0xbaf6bb50,0,0x37e3367c,0x3c003c00,0xba0fba8a,0,0x393a389b,
0x3bc33bfe,0xbb77bbfa,0xb3c6aa48,0x35c22cb5,0x3a6d3b3b,0xb89bba4f,0xb8c4b6d7,0x3a8a38ec,0x381d395f,0xa648b505,0xbaddb9ed,0x3bff3b99,
0x30b23564,0x38483444,0xbbeabb88,0x3ac23bb6,0x3b0e3bf6,0xba8abbf1,0xb78bae46,0x389b2fd6,0x34a53913,0x2648b732,0xbba8ba2f,0x3bff3b25,
0xb78bae46,0x3ac237e3,0xbb0ebbf6,0x38483af6,0xbba8ba2f,0x3b503bfa,0xb4a5b913,0xb67c2cb5,0x39ed3bea,0xb93abbe2,0xb95fb0b2,0x3a0f3179,
0xb56433c6,0x38eca648,0xbb88bbc3,0x3a4f3bff,0xbbfeba6d,0x3b253bce,0xaa48b8c4,0xb7323303,0xb6d7badd,0xb444367c,0x3b3b381d,0xbbb6bb50,
0x38723bd9,0xb732bbce,0xbaa7b23e,0x3b253303,0xbaa7b23e,0x3bb6367c,0xb872bbd9,0x34443b50,0xb872bbd9,0x2cb53a8a,0x3aa7323e,0xbbfab89b,
0x3aa7323e,0xbbf1b9cb,0x38723bd9,0x2fd6b984,0x35643bc3,0xb303bbb6,0xbb88b3c6,0x3bce3444,0xbbfeb8c4,0x3b773a0f,0x2a48ba6d,0xb5c2393a,
0x36d7b81d,0xba8a2fd6,0x3b3b3add,0xb89bbbf1,0x395f3bea,0xa648bb25,0xb9ed30b2,0x3bff3732,0x2e463ba8,0x2648bb99,0xbbf6b4a5,0x3bff3505,
0xba2fbb0e,0x38483bb6,0x3913b78b,0xbac23444,0x3bf634a5,0xbb50b93a,0x2e463ba8,0x367cba0f,0xb913378b,0x3be22fd6,0xba2fbb0e,0x31793bf1,
0xb0b23b88,0x3444bb77,0xbbeab564,0x3bb635c2,0xb3c6bbfe,0xacb53be2,0x3bc3aa48,0xbbfab179,0x38c43b3b,0xafd6bbff,0xba6d36d7,0x3bf1a648,
0xbaddb95f,0x35053bce,0x381db9ed,0xbb993303,0xb61f3b64,0x37e3bb50,0xbb64b61f,0x3af6367c,0x361fbb64,0xb93a3a8a,0x3b64361f,0xba0fb89b,
0xb61f3b64,0x3a4fb984,0xbb64b61f,0x38ec39cb,0x361fbb64,0xbb253848,0x3b64361f,0xb732bac2,0xb8c43b3b,0x3984bb25,0xba6db6d7,0x39cb3732,
0x3addb95f,0xbbce37e3,0x381d39ed,0xb303baf6,0xbbea3564,0x3b772cb5,0xb0b2bb88,0xb5c23bfa,0x3bc32a48,0xb89bb8ec,0xb3c63bfe,0x3a8aba4f,
0xba2f3b0e,0x3ac2baf6,0xb913b78b,0x384837e3,0x3bf6b4a5,0xbb502cb5,0xae463ba8,0x367cbbfa,0xb913b78b,0x31793a4f,0x3a2fbb0e,0xbbe238ec,
0xae463ba8,0x39cbbb99,0xbbf634a5,0x39843505,0xbb3b3add,0x3b99bac2,0xb6d7b81d,0x35053848,0x39ed30b2,0xb7e3b5c2,0xb95f3bea,0x3af6bb77,
0x3564bbc3,0xba0f3be2,0x3b88b3c6,0xb93ab179,0xbbfe38c4,0x3a4fa648,0xaa48ba6d,0xb8ec3bff,0xbbd93aa7,0x3bfaba8a,0xb23eb872,0x2cb5389b,
0x323e3872,0x2fd6b9cb,0xbbd93aa7,0x3bf1b984,0x3bd9baa7,0xbb993848,0x323e3872,0x3505bac2,0xb23eb872,0xb7e33b77,0x3bd9baa7,0xbaf635c2,
0xbbfe3a6d,0x3be2ba4f,0x2a48b8c4,0xb17938ec,0xb6d73add,0x3984bb99,0xbb3b381d,0x39cbb505,0x395fb0b2,0xb303b444,0xb9ed3bea,0x3bcebbb6,
0x3b88bbc3,0xbb77393a,0x356433c6,0x35c2ba0f,0xbba83a2f,0x3b50ba0f,0x34a5b913,0xb67c393a,0xbb0e3bf6,0x3be2bbf1,0xb78b2e46,0x31792fd6,
0xb4a53913,0x39cbbb25,0xbba83a2f,0x3984b732,0x378bae46,0x3303b7e3,0xbb0e3bf6,0x3bcebaf6,0xbadd39ed,0x3a4fb9cb,0x381db95f,0xb8ec3984,
0xbbea3b88,0x3b25bac2,0x30b2b564,0xb7323848,0xbbc33bfe,0x3bb6bb77,0xb3c62a48,0xb44435c2,0xba6d3b3b,0x3bfabbe2,0xb8c436d7,0xacb53179,
0xb9a839a8,0x38ecb984,0x39a8b9a8,0xba4f39cb,0xb9a839a8,0x3732b848,0x39a8b9a8,0xbb253ac2,0xb9a839a8,0x3444b5c2,0x39a8b9a8,0xbbb63b77,
0xb9a839a8,0x2cb5b179,0x39a8b9a8,0xbbfa3be2,0xb81d395f,0x367cb93a,0x3addb9ed,0xbb503a0f,0xb0b23564,0xb179afd6,0x3beabb88,0xbbe23bf1,
0x33c6aa48,0xb9843732,0x3bc3bbfe,0xb9cb3b25,0x38c4b6d7,0xbbce3af6,0x3a6dbb3b,0xb30337e3,0xb4a53913,0x3179b8ec,0x3ba8ba2f,0xbbe23a4f,
0x378bae46,0xb9cb3505,0x3b0ebbf6,0xb9843b99,0x3ba8ba2f,0xbbce3bb6,0x34a5b913,0x33033444,0x3b0ebbf6,0xb5c23a0f,0xb78b2e46,0x3b77b93a,
0xaa4838c4,0xacb5b89b,0x3bfeba6d,0xbbfa3a8a,0x3b3bb81d,0xbbf13984,0x36d7badd,0xafd639cb,0x39edbbea,0xb5053ac2,0xb95f30b2,0x3b99b848,
0xb564b3c6,0x3af6b5c2,0xbb883bc3,0x37e3bb77,0x323e3872,0xb505b848,0x3bd9baa7,0xbb993ac2,0x3bd9baa7,0xbaf63b77,0xb23eb872,0x37e335c2,
0xb23eb872,0x393a3179,0xbbd93aa7,0x3a0fbbe2,0xbbd93aa7,0x38ecbbff,0x323e3872,0xba4f2648,0x36d7381d,0xb848b7e3,0x3b3bbadd,0xbac23af6,
0x395fbbea,0xb67c3bfa,0xb9edb0b2,0x3b50acb5,0xbb8833c6,0x3be2b8ec,0xb5643bc3,0xb179ba4f,0x2a483a6d,0xb984b505,0x3bfeb8c4,0xb9cb3b99,
0x3913378b,0xb9cbb732,0x3a2fbb0e,0xb9843b25,0x2e46bba8,0x33033af6,0xbbf634a5,0x3bceb7e3,0xba2f3b0e,0x35c2bbfa,0x3913378b,0xbb77acb5,
0x3bf6b4a5,0xba8a3a4f,0x2e46bba8,0x389b38ec,0x3a6d36d7,0xbaf6b67c,0x38c4bb3b,0xb7e33b50,0xb81db9ed,0x3a0f389b,0xbadd395f,0x393aba8a,
0x30b23b88,0xb8ecb9cb,0x3beab564,0xba4f3984,0x33c6bbfe,0x37323ac2,0xbbc3aa48,0x3b25b848,0x3b64361f,0xbbb6b5c2,0x361fbb64,0xb4443b77,
0xbb64b61f,0x3bfa3179,0xb61f3b64,0x2cb5bbe2,0x3b64361f,0xbbf12648,0x361fbb64,0x2fd63bff,0xbb64b61f,0x3b99b303,0xb61f3b64,0xb505bbce,
0x3bea3564,0xbbffb505,0x30b2bb88,0xa6483b99,0xbbc32a48,0x3ac2b444,0x33c63bfe,0xb848bbb6,0x3a6db6d7,0xb67c3a0f,0xb8c4bb3b,0x3b50393a,
0xb81d39ed,0xb179bbf1,0x3add395f,0xbbe2afd6,0x3bf634a5,0xbbceb444,0xae46bba8,0x33033bb6,0xb913378b,0x35c2b93a,0x3a2f3b0e,0xbb77ba0f,
0xae46bba8,0x389b3bf1,0xbbf6b4a5,0x3a8aafd6,0x3a2f3b0e,0xbbffb732,0x3913b78b,0x26483b25,0x3b8833c6,0xbb25b303,0xb564bbc3,0x37323bce,
0xaa483a6d,0xb444bb50,0x3bfe38c4,0xbbb6b67c,0xbb3bbadd,0x3bfa389b,0xb6d7381d,0xacb5ba8a,0x39edb0b2,0xafd63984,0xb95fbbea,0x3bf139cb,
0x3aa7323e,0xba0fb179,0xb872bbd9,0x393a3be2,0x38723bd9,0xba4fbbff,0x3aa7323e,0xb8ec2648,0xbaa7b23e,0x3732b303,0x38723bd9,0xbb25bbce,
0xb872bbd9,0x3bb63b50,0xbaa7b23e,0x3444b67c,0x395f30b2,0xb89bafd6,0xb9edbbea,0x3a8a3bf1,0x3b883bc3,0xbbffbb25,0x3564b3c6,0xa6483732,
0x2a4838c4,0xb848baf6,0x3bfe3a6d,0xbac2b7e3,0xbb3bb81d,0x367cacb5,0x36d73add,0xbb50bbfa,0x378b2e46,0xb5c2acb5,0xbb0ebbf6,0x3b773bfa,
0x3ba83a2f,0xba8ab8ec,0xb4a5b913,0x389b3a4f,0x3b0e3bf6,0xbbffbb99,0x378b2e46,0x26483505,0x34a53913,0xbac2bbb6,0x3ba83a2f,0xb848b444,
0x33c62a48,0xafd6a648,0xbbc3bbfe,0x3bf13bff,0x38c436d7,0xb505b303,0xba6dbb3b,0x3b993bce,0x3add39ed,0xb7e3b67c,0xb81db95f,0x3af63b50,
0x3bea3b88,0xb93ab89b,0xb0b2b564,0x3a0f3a8a,0x3c003c00,0x38ec3984,0,0xba4fb9cb,0x3c003c00,0x37323848,0,0xbb25bac2,
0x3c003c00,0x344435c2,0,0xbbb6bb77,0x3c003c00,0x2cb53179,0,0xbbfabbe2,0xb3c6aa48,0xbb50ba0f,0xbbc3bbfe,0xb67cb93a,
0xb8c4b6d7,0xbbe2bbf1,0xba6dbb3b,0x3179afd6,0xbaddb9ed,0xb9cbbb25,0xb81db95f,0x39843732,0xbbeabb88,0xb303b7e3,0xb0b2b564,0x3bce3af6,
0xbb0ebbf6,0xb179b8ec,0x378b2e46,0x3be23a4f,0xb4a5b913,0x39cb3505,0x3ba83a2f,0x39843b99,0x378b2e46,0x3bce3bb6,0x3b0e3bf6,0xb3033444,
0x3ba83a2f,0x35c23a0f,0x34a53913,0xbb77b93a,0x395f30b2,0x3bfa3a8a,0x39ed3bea,0xacb5389b,0x3b883bc3,0x2fd639cb,0xb56433c6,0xbbf1b984,
0x2a4838c4,0xbb99b848,0xbbfeba6d,0xb505bac2,0xbb3bb81d,0xb7e3bb77,0xb6d7badd,0x3af635c2,0x38723bd9,0xb5053848,0xbaa7b23e,0xbb99bac2,
0xbaa7b23e,0xbaf6bb77,0xb872bbd9,0x37e3b5c2,0xb872bbd9,0x393ab179,0x3aa7323e,0x3a0f3be2,0x3aa7323e,0x38ec3bff,0x38723bd9,0xba4fa648,
0xbb88b3c6,0xbac2baf6,0xb564bbc3,0x3848b7e3,0x2a48ba6d,0x3b502cb5,0x3bfe38c4,0x367c3bfa,0x3b3b3add,0xb1793a4f,0xb6d7381d,0xbbe2b8ec,
0xb9ed30b2,0xb9cbbb99,0xb95fbbea,0x3984b505,0xae46bba8,0x39cbb732,0x3bf634a5,0x39843b25,0x3a2f3b0e,0xb3033af6,0xb913378b,0xbbceb7e3,
0xbbf6b4a5,0xb5c2bbfa,0xae46bba8,0x3b77acb5,0x3913b78b,0x3a8a3a4f,0x3a2f3b0e,0xb89b38ec,0x3bea3564,0x37e33b50,0xb0b23b88,0xbaf6367c,
0xbbc32a48,0xb93aba8a,0xb3c6bbfe,0x3a0fb89b,0x3a6db6d7,0x3a4f3984,0x38c43b3b,0xb8ec39cb,0xb81d39ed,0xbb25b848,0xbaddb95f,0x3732bac2,
0xb61f3b64,0xbbb635c2,0xbb64b61f,0xb444bb77,0x361fbb64,0x3bfab179,0x3b64361f,0x2cb53be2,0xb61f3b64,0xbbf1a648,0xbb64b61f,0x2fd6bbff,
0x361fbb64,0x3b993303,0x3b64361f,0xb5053bce,0xba6db6d7,0xa648bb99,0x38c4bb3b,0x3bffb505,0x381d39ed,0xb8483bb6,0xbadd395f,0xbac2b444,
0xb0b2bb88,0x3b50b93a,0x3beab564,0x367c3a0f,0xb3c63bfe,0xbbe22fd6,0xbbc3aa48,0x3179bbf1,0x3a2fbb0e,0x3bceb444,0x3913378b,0xb3033bb6,
0xbbf634a5,0xb5c2b93a,0x2e46bba8,0x3b77ba0f,0x3913378b,0xb89b3bf1,0xba2f3b0e,0xba8aafd6,0x2e46bba8,0x3bffb732,0x3bf6b4a5,0xa6483b25,
0x36d7381d,0xb7323bce,0xbb3b3add,0xbb253303,0x395fbbea,0x3bb6b67c,0x39ed30b2,0xb4443b50,0xbb8833c6,0x2cb5ba8a,0x3564bbc3,0x3bfab89b,
0x2a483a6d,0xbbf139cb,0xbbfe38c4,0xafd6b984,0xbbd93aa7,0xba0f3179,0xb23eb872,0x393abbe2,0x323e3872,0xba4f3bff,0xbbd93aa7,0xb8eca648,
0x3bd9baa7,0x37323303,0x323e3872,0xbb253bce,0xb23eb872,0x3bb6bb50,0x3bd9baa7,0x3444367c,0x2a48b8c4,0x3a8abbf1,0x3bfeba6d,0x389bafd6,
0xbb3b381d,0xa648b732,0x36d7badd,0x3bffbb25,0xb9ed3bea,0xbac237e3,0xb95f30b2,0x3848baf6,0x356433c6,0xbb503bfa,0xbb883bc3,0xb67cacb5,
0x3ba8ba2f,0x35c2acb5,0xb4a53913,0xbb773bfa,0x3b0ebbf6,0x3a8ab8ec,0x378bae46,0xb89b3a4f,0x34a5b913,0x3bffbb99,0x3ba8ba2f,0xa6483505,
0xb78b2e46,0x3ac2bbb6,0x3b0ebbf6,0x3848b444,0xb81d395f,0xbbf13bff,0xbadd39ed,0xafd62648,0xb0b23564,0xbb993bce,0xbbea3b88,0xb5053303,
0x33c6aa48,0xbaf63b50,0xbbc33bfe,0xb7e3367c,0x38c4b6d7,0xba0f3a8a,0xba6d3b3b,0xb93a389b,0xb9a839a8,0x2fd6a648,0x39a8b9a8,0x3bf1bbff,
0xb9a839a8,0x3505b303,0x39a8b9a8,0x3b99bbce,0xb9a839a8,0x37e3b67c,0x39a8b9a8,0x3af6bb50,0xb9a839a8,0x393ab89b,0x39a8b9a8,0x3a0fba8a,
0x3addb9ed,0x3b77bbfa,0x381db95f,0xb5c22cb5,0x3beabb88,0x389bba4f,0x30b2b564,0xba8a38ec,0x3bc3bbfe,0x2648b505,0xb3c62a48,0xbbff3b99,
0x3a6dbb3b,0xb8483444,0xb8c436d7,0xbac23bb6,0x34a5b913,0xb89b2fd6,0xbba83a2f,0xba8a3bf1,0xb78b2e46,0xbbff3b25,0xbb0e3bf6,0x26483732,
0xbba83a2f,0xb8483af6,0xb4a53913,0x3ac2b7e3,0xbb0e3bf6,0x367c2cb5,0x378bae46,0x3b50bbfa,0xbbfe3a6d,0xb93a3be2,0xaa4838c4,0x3a0fb179,
0xb6d73add,0x38ec2648,0x3b3bb81d,0x3a4fbbff,0x395fb0b2,0x3b25bbce,0x39edbbea,0xb732b303,0x3b88bbc3,0xb444b67c,0xb564b3c6,0xbbb63b50,
0x323e3872,0x3b25b303,0x3bd9baa7,0x3732bbce,0x3bd9baa7,0x3444bb50,0xb23eb872,0xbbb6367c,0xb23eb872,0xbbfa389b,0xbbd93aa7,0xacb53a8a,
0xbbd93aa7,0x2fd63984,0x323e3872,0x3bf1b9cb,0x3b3bbadd,0x3303bbb6,0xb6d7b81d,0xbbce3444,0xb9edb0b2,0xbb773a0f,0xb95f3bea,0x35c2393a,
0xb5643bc3,0x3a8a2fd6,0x3b88b3c6,0x389bbbf1,0x3bfeb8c4,0x2648bb25,0xaa48ba6d,0xbbff3732,0xb913b78b,0xbbff3505,0xba2f3b0e,0x26483b99,
0xae463ba8,0x3ac23444,0x3bf6b4a5,0x3848bbb6,0x3a2fbb0e,0xb67cba0f,0xb913b78b,0xbb50393a,0xbbf634a5,0xb1793bf1,0xae463ba8,0x3be2afd6,
0xb8c43b3b,0x34443b77,0x3a6d36d7,0x3bb6b5c2,0x3addb95f,0xacb5bbe2,0xb81db9ed,0xbbfa3179,0xbbea3564,0xafd63bff,0x30b23b88,0x3bf12648,
0x3bc32a48,0x3505bbce,0x33c6bbfe,0xbb99b303,0x3b64361f,0x3af6b67c,0x361fbb64,0xb7e3bb50,0xbb64b61f,0xba0f389b,0xb61f3b64,0x393a3a8a,
0x3b64361f,0x38ecb9cb,0x361fbb64,0xba4fb984,0xbb64b61f,0xb7323ac2,0xb61f3b64,0x3b253848,0x30b2bb88,0xb984bb25,0xbbeab564,0xb9cb3732,
0x33c63bfe,0x3bce37e3,0x3bc3aa48,0x3303baf6,0xb8c4bb3b,0xbb772cb5,0xba6d36d7,0x35c23bfa,0x3add395f,0x389bb8ec,0x381db9ed,0xba8aba4f,
0xbbf6b4a5,0xb84837e3,0x2e463ba8,0x3ac23af6,0x3913b78b,0xb67cbbfa,0xba2fbb0e,0xbb50acb5,0x2e463ba8,0x3be238ec,0x3bf634a5,0x3179ba4f,
0xba2fbb0e,0xb9843505,0xb913378b,0x39cb3b99,0x35643bc3,0x3b993ac2,0x3b8833c6,0x3505b848,0xbbfeb8c4,0xb7e335c2,0xaa483a6d,0x3af63b77,
0x36d7b81d,0xba0fbbe2,0xbb3bbadd,0xb93a3179,0x395f3bea,0x3a4f2648,0x39edb0b2,0xb8ecbbff,0x3aa7323e,0x2cb5b89b,0xb872bbd9,0xbbfaba8a,
0x38723bd9,0x3bf13984,0x3aa7323e,0xafd6b9cb,0xbaa7b23e,0x35053ac2,0x38723bd9,0x3b993848,0xb872bbd9,0xbaf6b5c2,0xbaa7b23e,0x37e33b77,
0xb9edbbea,0xbbe2ba4f,0xb95fb0b2,0x317938ec,0x3564b3c6,0xb984bb99,0xbb88bbc3,0xb9cbb505,0x3bfe3a6d,0x3303b444,0xaa48b8c4,0xbbcebbb6,
0x36d73add,0x3b77393a,0x3b3b381d,0xb5c2ba0f,0xb78bae46,0x367c393a,0x3b0e3bf6,0x3b503a0f,0xbba8ba2f,0xb1792fd6,0x34a53913,0x3be23bf1,
0xbb0ebbf6,0xb984b732,0xb78bae46,0x39cb3b25,0xb4a5b913,0xbbcebaf6,0xbba8ba2f,0x330337e3,0x3bc33bfe,0x3a4f39cb,0x33c62a48,0xb8ecb984,
0x3a6d3b3b,0x3b253ac2,0x38c436d7,0xb732b848,0x381d395f,0x3bb63b77,0x3add39ed,0xb444b5c2,0x30b23564,0x3bfa3be2,0x3bea3b88,0xacb5b179,
0x3c003c00,0xb8ecb984,0,0x3a4f39cb,0x3c003c00,0xb732b848,0,0x3b253ac2,0x3c003c00,0xb444b5c2,0,0x3bb63b77,
0x3c003c00,0xacb5b179,0,0x3bfa3be2,0xb3c6aa48,0x3b503a0f,0xbbc3bbfe,0x367c393a,0xb8c4b6d7,0x3be23bf1,0xba6dbb3b,0xb1792fd6,
0xbaddb9ed,0x39cb3b25,0xb81db95f,0xb984b732,0xbbeabb88,0x330337e3,0xb0b2b564,0xbbcebaf6,0xbb0ebbf6,0x317938ec,0x378b2e46,0xbbe2ba4f,
0xb4a5b913,0xb9cbb505,0x3ba83a2f,0xb984bb99,0x378b2e46,0xbbcebbb6,0x3b0e3bf6,0x3303b444,0x3ba83a2f,0xb5c2ba0f,0x34a53913,0x3b77393a,
0x395f30b2,0xbbfaba8a,0x39ed3bea,0x2cb5b89b,0x3b883bc3,0xafd6b9cb,0xb56433c6,0x3bf13984,0x2a4838c4,0x3b993848,0xbbfeba6d,0x35053ac2,
0xbb3bb81d,0x37e33b77,0xb6d7badd,0xbaf6b5c2,0x38723bd9,0x3505b848,0xbaa7b23e,0x3b993ac2,0xbaa7b23e,0x3af63b77,0xb872bbd9,0xb7e335c2,
0xb872bbd9,0xb93a3179,0x3aa7323e,0xba0fbbe2,0x3aa7323e,0xb8ecbbff,0x38723bd9,0x3a4f2648,0xbb88b3c6,0x3ac23af6,0xb564bbc3,0xb84837e3,
0x2a48ba6d,0xbb50acb5,0x3bfe38c4,0xb67cbbfa,0x3b3b3add,0x3179ba4f,0xb6d7381d,0x3be238ec,0xb9ed30b2,0x39cb3b99,0xb95fbbea,0xb9843505,
0xae46bba8,0xb9cb3732,0x3bf634a5,0xb984bb25,0x3a2f3b0e,0x3303baf6,0xb913378b,0x3bce37e3,0xbbf6b4a5,0x35c23bfa,0xae46bba8,0xbb772cb5,
0x3913b78b,0xba8aba4f,0x3a2f3b0e,0x389bb8ec,0x3bea3564,0xb7e3bb50,0xb0b23b88,0x3af6b67c,0xbbc32a48,0x393a3a8a,0xb3c6bbfe,0xba0f389b,
0x3a6db6d7,0xba4fb984,0x38c43b3b,0x38ecb9cb,0xb81d39ed,0x3b253848,0xbaddb95f,0xb7323ac2,0xb61f3b64,0x3bb6b5c2,0xbb64b61f,0x34443b77,
0x361fbb64,0xbbfa3179,0x3b64361f,0xacb5bbe2,0xb61f3b64,0x3bf12648,0xbb64b61f,0xafd63bff,0x361fbb64,0xbb99b303,0x3b64361f,0x3505bbce,
0xba6db6d7,0x26483b99,0x38c4bb3b,0xbbff3505,0x381d39ed,0x3848bbb6,0xbadd395f,0x3ac23444,0xb0b2bb88,0xbb50393a,0x3beab564,0xb67cba0f,
0xb3c63bfe,0x3be2afd6,0xbbc3aa48,0xb1793bf1,0x3a2fbb0e,0xbbce3444,0x3913378b,0x3303bbb6,0xbbf634a5,0x35c2393a,0x2e46bba8,0xbb773a0f,
0x3913378b,0x389bbbf1,0xba2f3b0e,0x3a8a2fd6,0x2e46bba8,0xbbff3732,0x3bf6b4a5,0x2648bb25,0x36d7381d,0x3732bbce,0xbb3b3add,0x3b25b303,
0x395fbbea,0xbbb6367c,0x39ed30b2,0x3444bb50,0xbb8833c6,0xacb53a8a,0x3564bbc3,0xbbfa389b,0x2a483a6d,0x3bf1b9cb,0xbbfe38c4,0x2fd63984,
0xbbd93aa7,0x3a0fb179,0xb23eb872,0xb93a3be2,0x323e3872,0x3a4fbbff,0xbbd93aa7,0x38ec2648,0x3bd9baa7,0xb732b303,0x323e3872,0x3b25bbce,
0xb23eb872,0xbbb63b50,0x3bd9baa7,0xb444b67c,0x2a48b8c4,0xba8a3bf1,0x3bfeba6d,0xb89b2fd6,0xbb3b381d,0x26483732,0x36d7badd,0xbbff3b25,
0xb9ed3bea,0x3ac2b7e3,0xb95f30b2,0xb8483af6,0x356433c6,0x3b50bbfa,0xbb883bc3,0x367c2cb5,0x3ba8ba2f,0xb5c22cb5,0xb4a53913,0x3b77bbfa,
0x3b0ebbf6,0xba8a38ec,0x378bae46,0x389bba4f,0x34a5b913,0xbbff3b99,0x3ba8ba2f,0x2648b505,0xb78b2e46,0xbac23bb6,0x3b0ebbf6,0xb8483444,
0xb81d395f,0x3bf1bbff,0xbadd39ed,0x2fd6a648,0xb0b23564,0x3b99bbce,0xbbea3b88,0x3505b303,0x33c6aa48,0x3af6bb50,0xbbc33bfe,0x37e3b67c,
0x38c4b6d7,0x3a0fba8a,0xba6d3b3b,0x393ab89b,0xb9a839a8,0xafd62648,0x39a8b9a8,0xbbf13bff,0xb9a839a8,0xb5053303,0x39a8b9a8,0xbb993bce,
0xb9a839a8,0xb7e3367c,0x39a8b9a8,0xbaf63b50,0xb9a839a8,0xb93a389b,0x39a8b9a8,0xba0f3a8a,0x3addb9ed,0xbb773bfa,0x381db95f,0x35c2acb5,
0x3beabb88,0xb89b3a4f,0x30b2b564,0x3a8ab8ec,0x3bc3bbfe,0xa6483505,0xb3c62a48,0x3bffbb99,0x3a6dbb3b,0x3848b444,0xb8c436d7,0x3ac2bbb6,
0x34a5b913,0x389bafd6,0xbba83a2f,0x3a8abbf1,0xb78b2e46,0x3bffbb25,0xbb0e3bf6,0xa648b732,0xbba83a2f,0x3848baf6,0xb4a53913,0xbac237e3,
0xbb0e3bf6,0xb67cacb5,0x378bae46,0xbb503bfa,0xbbfe3a6d,0x393abbe2,0xaa4838c4,0xba0f3179,0xb6d73add,0xb8eca648,0x3b3bb81d,0xba4f3bff,
0x395fb0b2,0xbb253bce,0x39edbbea,0x37323303,0x3b88bbc3,0x3444367c,0xb564b3c6,0x3bb6bb50,0x323e3872,0xbb253303,0x3bd9baa7,0xb7323bce,
0x3bd9baa7,0xb4443b50,0xb23eb872,0x3bb6b67c,0xb23eb872,0x3bfab89b,0xbbd93aa7,0x2cb5ba8a,0xbbd93aa7,0xafd6b984,0x323e3872,0xbbf139cb,
0x3b3bbadd,0xb3033bb6,0xb6d7b81d,0x3bceb444,0xb9edb0b2,0x3b77ba0f,0xb95f3bea,0xb5c2b93a,0xb5643bc3,0xba8aafd6,0x3b88b3c6,0xb89b3bf1,
0x3bfeb8c4,0xa6483b25,0xaa48ba6d,0x3bffb732,0xb913b78b,0x3bffb505,0xba2f3b0e,0xa648bb99,0xae463ba8,0xbac2b444,0x3bf6b4a5,0xb8483bb6,
0x3a2fbb0e,0x367c3a0f,0xb913b78b,0x3b50b93a,0xbbf634a5,0x3179bbf1,0xae463ba8,0xbbe22fd6,0xb8c43b3b,0xb444bb77,0x3a6d36d7,0xbbb635c2,
0x3addb95f,0x2cb53be2,0xb81db9ed,0x3bfab179,0xbbea3564,0x2fd6bbff,0x30b23b88,0xbbf1a648,0x3bc32a48,0xb5053bce,0x33c6bbfe,0x3b993303,
0x3b64361f,0xbaf6367c,0x361fbb64,0x37e33b50,0xbb64b61f,0x3a0fb89b,0xb61f3b64,0xb93aba8a,0x3b64361f,0xb8ec39cb,0x361fbb64,0x3a4f3984,
0xbb64b61f,0x3732bac2,0xb61f3b64,0xbb25b848,0x30b2bb88,0x39843b25,0xbbeab564,0x39cbb732,0x33c63bfe,0xbbceb7e3,0x3bc3aa48,0xb3033af6,
0xb8c4bb3b,0x3b77acb5,0xba6d36d7,0xb5c2bbfa,0x3add395f,0xb89b38ec,0x381db9ed,0x3a8a3a4f,0xbbf6b4a5,0x3848b7e3,0x2e463ba8,0xbac2baf6,
0x3913b78b,0x367c3bfa,0xba2fbb0e,0x3b502cb5,0x2e463ba8,0xbbe2b8ec,0x3bf634a5,0xb1793a4f,0xba2fbb0e,0x3984b505,0xb913378b,0xb9cbbb99,
0x35643bc3,0xbb99bac2,0x3b8833c6,0xb5053848,0xbbfeb8c4,0x37e3b5c2,0xaa483a6d,0xbaf6bb77,0x36d7b81d,0x3a0f3be2,0xbb3bbadd,0x393ab179,
0x395f3bea,0xba4fa648,0x39edb0b2,0x38ec3bff,0x3aa7323e,0xacb5389b,0xb872bbd9,0x3bfa3a8a,0x38723bd9,0xbbf1b984,0x3aa7323e,0x2fd639cb,
0xbaa7b23e,0xb505bac2,0x38723bd9,0xbb99b848,0xb872bbd9,0x3af635c2,0xbaa7b23e,0xb7e3bb77,0xb9edbbea,0x3be23a4f,0xb95fb0b2,0xb179b8ec,
0x3564b3c6,0x39843b99,0xbb88bbc3,0x39cb3505,0x3bfe3a6d,0xb3033444,0xaa48b8c4,0x3bce3bb6,0x36d73add,0xbb77b93a,0x3b3b381d,0x35c23a0f,
0xb78bae46,0xb67cb93a,0x3b0e3bf6,0xbb50ba0f,0xbba8ba2f,0x3179afd6,0x34a53913,0xbbe2bbf1,0xbb0ebbf6,0x39843732,0xb78bae46,0xb9cbbb25,
0xb4a5b913,0x3bce3af6,0xbba8ba2f,0xb303b7e3,0x3bc33bfe,0xba4fb9cb,0x33c62a48,0x38ec3984,0x3a6d3b3b,0xbb25bac2,0x38c436d7,0x37323848,
0x381d395f,0xbbb6bb77,0x3add39ed,0x344435c2,0x30b23564,0xbbfabbe2,0x3bea3b88,0x2cb53179,0x3c003c00,0xafd6a648,0,0xbbf1bbff,
0x3c003c00,0xb505b303,0,0xbb99bbce,0x3c003c00,0xb7e3b67c,0,0xbaf6bb50,0x3c003c00,0xb93ab89b,0,0xba0fba8a,
0xbbc3bbfe,0x35c22cb5,0x33c62a48,0x3b773bfa,0xba6dbb3b,0x3a8a38ec,0x38c436d7,0x389b3a4f,0xb81db95f,0x3bff3b99,0x3add39ed,0x26483505,
0xb0b2b564,0x3ac23bb6,0x3bea3b88,0xb848b444,0x3b0e3bf6,0xb89bafd6,0xb78bae46,0xba8abbf1,0x34a53913,0xbbffbb25,0xbba8ba2f,0x2648b732,
0xb78bae46,0xb848baf6,0xbb0ebbf6,0x3ac237e3,0xbba8ba2f,0x367cacb5,0xb4a5b913,0x3b503bfa,0xb9edbbea,0x3a0f3179,0x395f30b2,0x393a3be2,
0x3564b3c6,0x3a4f3bff,0x3b883bc3,0xb8ec2648,0x3bfe3a6d,0xb7323303,0x2a4838c4,0xbb25bbce,0x36d73add,0xbbb6bb50,0xbb3bb81d,0x3444b67c,
0x38723bd9,0xbb25b303,0xbaa7b23e,0xb732bbce,0xbaa7b23e,0xb444bb50,0xb872bbd9,0x3bb6367c,0xb872bbd9,0x3bfa389b,0x3aa7323e,0x2cb53a8a,
0x3aa7323e,0xafd63984,0x38723bd9,0xbbf1b9cb,0xb564bbc3,0x3bce3444,0x3b8833c6,0x33033bb6,0x3bfe38c4,0xb5c2393a,0xaa483a6d,0xbb77ba0f,
0xb6d7381d,0xb89bbbf1,0xbb3bbadd,0x3a8aafd6,0xb95fbbea,0x3bff3732,0x39edb0b2,0x26483b25,0x2e463ba8,0xbbffb505,0xbbf6b4a5,0x2648bb99,
0xba2fbb0e,0x3ac2b444,0x3913b78b,0x38483bb6,0x3bf634a5,0xb67c3a0f,0x2e463ba8,0xbb50b93a,0xb913378b,0xb179bbf1,0xba2fbb0e,0x3be22fd6,
0x30b2bb88,0x3bb635c2,0x3bea3564,0xb4443b77,0x33c63bfe,0xbbfab179,0xbbc32a48,0x2cb5bbe2,0xb8c4bb3b,0x3bf1a648,0x3a6db6d7,0x2fd63bff,
0x3add395f,0xbb993303,0xb81d39ed,0xb505bbce,0xb61f3b64,0xbaf6b67c,0xbb64b61f,0x37e3bb50,0x361fbb64,0x3a0f389b,0x3b64361f,0xb93a3a8a,
0xb61f3b64,0xb8ecb9cb,0xbb64b61f,0x3a4fb984,0x361fbb64,0x37323ac2,0x3b64361f,0xbb253848,0x38c4bb3b,0x39cb3732,0x3a6d36d7,0xb9843b25,
0xbadd395f,0xb303baf6,0xb81db9ed,0x3bceb7e3,0x3beab564,0xb5c23bfa,0x30b23b88,0xbb77acb5,0xbbc3aa48,0x3a8aba4f,0x33c6bbfe,0x389b38ec,
0xba2f3b0e,0xb848b7e3,0xb913b78b,0x3ac2baf6,0x3bf6b4a5,0xb67c3bfa,0xae463ba8,0xbb502cb5,0xb913b78b,0x3be2b8ec,0x3a2fbb0e,0x31793a4f,
0xae463ba8,0xb984b505,0xbbf634a5,0x39cbbb99,0x3b3bbadd,0x35053848,0x36d7381d,0xbb993ac2,0xb9edb0b2,0x3af6bb77,0x395fbbea,0x37e335c2,
0xb5643bc3,0xb93ab179,0xbb8833c6,0x3a0fbbe2,0x3bfeb8c4,0xb8ec3bff,0x2a483a6d,0xba4f2648,0xbbd93aa7,0xacb5b89b,0xb23eb872,0x3bfaba8a,
0x323e3872,0xbbf13984,0xbbd93aa7,0x2fd6b9cb,0x3bd9baa7,0xb5053ac2,0x323e3872,0xbb993848,0xb23eb872,0x3af6b5c2,0x3bd9baa7,0xb7e33b77,
0x3bfeba6d,0xb17938ec,0xaa4838c4,0xbbe23a4f,0x36d7badd,0x39cbb505,0x3b3bb81d,0xb9843b99,0xb95f30b2,0x3bcebbb6,0x39edbbea,0x33033444,
0xbb883bc3,0x35c2ba0f,0xb564b3c6,0x3b77b93a,0xbba83a2f,0x367cb93a,0x34a5b913,0x3b50ba0f,0xbb0e3bf6,0xb179afd6,0xb78b2e46,0x3be2bbf1,
0xb4a53913,0xb9843732,0xbba83a2f,0x39cbbb25,0x378bae46,0xbbce3af6,0xbb0e3bf6,0x3303b7e3,0x3addb9ed,0xb8ec3984,0xb81d395f,0xba4f39cb,
0x3beabb88,0xb7323848,0xb0b23564,0xbb253ac2,0x3bc3bbfe,0xb44435c2,0x33c6aa48,0xbbb63b77,0x3a6dbb3b,0xacb53179,0x38c4b6d7,0xbbfa3be2,
0xb9a839a8,0x3a4fb9cb,0x39a8b9a8,0x38ecb984,0xb9a839a8,0x3b25bac2,0x39a8b9a8,0x3732b848,0xb9a839a8,0x3bb6bb77,0x39a8b9a8,0x3444b5c2,
0xb9a839a8,0x3bfabbe2,0x39a8b9a8,0x2cb5b179,0x381db95f,0xbb503a0f,0xbadd39ed,0xb67c393a,0x30b2b564,0xbbe23bf1,0xbbea3b88,0x31792fd6,
0xb3c62a48,0xb9cb3b25,0xbbc33bfe,0x3984b732,0xb8c436d7,0xb30337e3,0xba6d3b3b,0x3bcebaf6,0xb4a53913,0x3be2ba4f,0x3ba8ba2f,0x3179b8ec,
0x378bae46,0x3984bb99,0x3b0ebbf6,0xb9cb3505,0x3ba8ba2f,0xb303b444,0x34a5b913,0xbbce3bb6,0x3b0ebbf6,0xbb77393a,0xb78b2e46,0xb5c23a0f,
0x2a48b8c4,0xbbfa3a8a,0xbbfe3a6d,0x2cb5389b,0xbb3b381d,0xafd639cb,0xb6d73add,0x3bf1b984,0xb9ed3bea,0x3b99b848,0x395fb0b2,0x3505bac2,
0x356433c6,0x37e3bb77,0x3b88bbc3,0xbaf635c2,0x323e3872,0x3b99bac2,0x3bd9baa7,0xb505b848,0x3bd9baa7,0xb7e3b5c2,0xb23eb872,0xbaf63b77,
0xb23eb872,0xba0f3be2,0xbbd93aa7,0x393a3179,0xbbd93aa7,0x3a4fa648,0x323e3872,0x38ecbbff,0xb6d7b81d,0xbac23af6,0xbb3b3add,0x384837e3,
0xb95f3bea,0x3b50acb5,0x39ed30b2,0x367cbbfa,0x3b88b3c6,0xb179ba4f,0x3564bbc3,0xbbe238ec,0xaa48ba6d,0xb9cb3b99,0xbbfe38c4,0x39843505,
0x3913378b,0x3984bb25,0x3a2fbb0e,0xb9cbb732,0x2e46bba8,0xbbce37e3,0xbbf634a5,0x33033af6,0xba2f3b0e,0x3b772cb5,0x3913378b,0x35c2bbfa,
0x3bf6b4a5,0xb89bb8ec,0x2e46bba8,0xba8a3a4f,0xba6db6d7,0xb7e33b50,0xb8c43b3b,0x3af6367c,0x381d39ed,0x393aba8a,0x3addb95f,0xba0fb89b,
0xb0b2bb88,0xba4f3984,0xbbea3564,0x38ec39cb,0xb3c63bfe,0x3b25b848,0x3bc32a48,0xb732bac2,0x3b64361f,0x3444bb77,0x361fbb64,0xbbb6b5c2,
0xbb64b61f,0xacb53be2,0xb61f3b64,0x3bfa3179,0x3b64361f,0xafd6bbff,0x361fbb64,0xbbf12648,0xbb64b61f,0x35053bce,0xb61f3b64,0x3b99b303,
0xbbeab564,0xa6483b99,0xb0b23b88,0x3bff3505,0x3bc3aa48,0xb848bbb6,0xb3c6bbfe,0xbac23444,0xba6d36d7,0x3b50393a,0x38c43b3b,0x367cba0f,
0x381db9ed,0xbbe2afd6,0xbaddb95f,0x31793bf1,0x3bf634a5,0xb303bbb6,0xae46bba8,0xbbceb444,0xb913378b,0x3b773a0f,0x3a2f3b0e,0x35c2b93a,
0xae46bba8,0xba8a2fd6,0xbbf6b4a5,0x389b3bf1,0x3a2f3b0e,0xa648bb25,0x3913b78b,0xbbffb732,0xbb88b3c6,0x37323bce,0x35643bc3,0x3b253303,
0x2a48ba6d,0xbbb6b67c,0xbbfeb8c4,0x34443b50,0x3b3b3add,0xacb5ba8a,0x36d7b81d,0xbbfab89b,0xb9ed30b2,0x3bf139cb,0x395f3bea,0x2fd6b984,
0x3aa7323e,0xb93abbe2,0xb872bbd9,0xba0fb179,0x38723bd9,0x38eca648,0x3aa7323e,0xba4fbbff,0xbaa7b23e,0x3b253bce,0x38723bd9,0x3732b303,
0xb872bbd9,0xb444367c,0xbaa7b23e,0x3bb63b50,0xb95fb0b2,0x3a8a3bf1,0x39ed3bea,0x389b2fd6,0xbb88bbc3,0xa6483732,0xb56433c6,0x3bff3b25,
0xaa48b8c4,0xbac2b7e3,0xbbfeba6d,0x38483af6,0x3b3b381d,0xbb50bbfa,0xb6d7badd,0xb67c2cb5,0x378b2e46,0xbb77bbfa,0xbb0ebbf6,0xb5c2acb5,
0x3ba83a2f,0xb89bba4f,0xb4a5b913,0xba8ab8ec,0x3b0e3bf6,0xa648b505,0x378b2e46,0xbbffbb99,0x34a53913,0x38483444,0x3ba83a2f,0xbac2bbb6,
0xb3c6aa48,0x3bf13bff,0x3bc33bfe,0x2fd62648,0xb8c4b6d7,0x3b993bce,0x3a6d3b3b,0x35053303,0xbaddb9ed,0x3af63b50,0x381d395f,0x37e3367c,
0xbbeabb88,0x3a0f3a8a,0x30b23564,0x393a389b,0x3c003c00,0x2fd62648,0,0x3bf13bff,0x3c003c00,0x35053303,0,0x3b993bce,
0x3c003c00,0x37e3367c,0,0x3af63b50,0x3c003c00,0x393a389b,0,0x3a0f3a8a,0xbbc3bbfe,0xb5c2acb5,0x33c62a48,0xbb77bbfa,
0xba6dbb3b,0xba8ab8ec,0x38c436d7,0xb89bba4f,0xb81db95f,0xbbffbb99,0x3add39ed,0xa648b505,0xb0b2b564,0xbac2bbb6,0x3bea3b88,0x38483444,
0x3b0e3bf6,0x389b2fd6,0xb78bae46,0x3a8a3bf1,0x34a53913,0x3bff3b25,0xbba8ba2f,0xa6483732,0xb78bae46,0x38483af6,0xbb0ebbf6,0xbac2b7e3,
0xbba8ba2f,0xb67c2cb5,0xb4a5b913,0xbb50bbfa,0xb9edbbea,0xba0fb179,0x395f30b2,0xb93abbe2,0x3564b3c6,0xba4fbbff,0x3b883bc3,0x38eca648,
0x3bfe3a6d,0x3732b303,0x2a4838c4,0x3b253bce,0x36d73add,0x3bb63b50,0xbb3bb81d,0xb444367c,0x38723bd9,0x3b253303,0xbaa7b23e,0x37323bce,
0xbaa7b23e,0x34443b50,0xb872bbd9,0xbbb6b67c,0xb872bbd9,0xbbfab89b,0x3aa7323e,0xacb5ba8a,0x3aa7323e,0x2fd6b984,0x38723bd9,0x3bf139cb,
0xb564bbc3,0xbbceb444,0x3b8833c6,0xb303bbb6,0x3bfe38c4,0x35c2b93a,0xaa483a6d,0x3b773a0f,0xb6d7381d,0x389b3bf1,0xbb3bbadd,0xba8a2fd6,
0xb95fbbea,0xbbffb732,0x39edb0b2,0xa648bb25,0x2e463ba8,0x3bff3505,0xbbf6b4a5,0xa6483b99,0xba2fbb0e,0xbac23444,0x3913b78b,0xb848bbb6,
0x3bf634a5,0x367cba0f,0x2e463ba8,0x3b50393a,0xb913378b,0x31793bf1,0xba2fbb0e,0xbbe2afd6,0x30b2bb88,0xbbb6b5c2,0x3bea3564,0x3444bb77,
0x33c63bfe,0x3bfa3179,0xbbc32a48,0xacb53be2,0xb8c4bb3b,0xbbf12648,0x3a6db6d7,0xafd6bbff,0x3add395f,0x3b99b303,0xb81d39ed,0x35053bce,
0xb61f3b64,0x3af6367c,0xbb64b61f,0xb7e33b50,0x361fbb64,0xba0fb89b,0x3b64361f,0x393aba8a,0xb61f3b64,0x38ec39cb,0xbb64b61f,0xba4f3984,
0x361fbb64,0xb732bac2,0x3b64361f,0x3b25b848,0x38c4bb3b,0xb9cbb732,0x3a6d36d7,0x3984bb25,0xbadd395f,0x33033af6,0xb81db9ed,0xbbce37e3,
0x3beab564,0x35c2bbfa,0x30b23b88,0x3b772cb5,0xbbc3aa48,0xba8a3a4f,0x33c6bbfe,0xb89bb8ec,0xba2f3b0e,0x384837e3,0xb913b78b,0xbac23af6,
0x3bf6b4a5,0x367cbbfa,0xae463ba8,0x3b50acb5,0xb913b78b,0xbbe238ec,0x3a2fbb0e,0xb179ba4f,0xae463ba8,0x39843505,0xbbf634a5,0xb9cb3b99,
0x3b3bbadd,0xb505b848,0x36d7381d,0x3b99bac2,0xb9edb0b2,0xbaf63b77,0x395fbbea,0xb7e3b5c2,0xb5643bc3,0x393a3179,0xbb8833c6,0xba0f3be2,
0x3bfeb8c4,0x38ecbbff,0x2a483a6d,0x3a4fa648,0xbbd93aa7,0x2cb5389b,0xb23eb872,0xbbfa3a8a,0x323e3872,0x3bf1b984,0xbbd93aa7,0xafd639cb,
0x3bd9baa7,0x3505bac2,0x323e3872,0x3b99b848,0xb23eb872,0xbaf635c2,0x3bd9baa7,0x37e3bb77,0x3bfeba6d,0x3179b8ec,0xaa4838c4,0x3be2ba4f,
0x36d7badd,0xb9cb3505,0x3b3bb81d,0x3984bb99,0xb95f30b2,0xbbce3bb6,0x39edbbea,0xb303b444,0xbb883bc3,0xb5c23a0f,0xb564b3c6,0xbb77393a,
0xbba83a2f,0xb67c393a,0x34a5b913,0xbb503a0f,0xbb0e3bf6,0x31792fd6,0xb78b2e46,0xbbe23bf1,0xb4a53913,0x3984b732,0xbba83a2f,0xb9cb3b25,
0x378bae46,0x3bcebaf6,0xbb0e3bf6,0xb30337e3,0x3addb9ed,0x38ecb984,0xb81d395f,0x3a4fb9cb,0x3beabb88,0x3732b848,0xb0b23564,0x3b25bac2,
0x3bc3bbfe,0x3444b5c2,0x33c6aa48,0x3bb6bb77,0x3a6dbb3b,0x2cb5b179,0x38c4b6d7,0x3bfabbe2,0xb9a839a8,0xba4f39cb,0x39a8b9a8,0xb8ec3984,
0xb9a839a8,0xbb253ac2,0x39a8b9a8,0xb7323848,0xb9a839a8,0xbbb63b77,0x39a8b9a8,0xb44435c2,0xb9a839a8,0xbbfa3be2,0x39a8b9a8,0xacb53179,
0x381db95f,0x3b50ba0f,0xbadd39ed,0x367cb93a,0x30b2b564,0x3be2bbf1,0xbbea3b88,0xb179afd6,0xb3c62a48,0x39cbbb25,0xbbc33bfe,0xb9843732,
0xb8c436d7,0x3303b7e3,0xba6d3b3b,0xbbce3af6,0xb4a53913,0xbbe23a4f,0x3ba8ba2f,0xb17938ec,0x378bae46,0xb9843b99,0x3b0ebbf6,0x39cbb505,
0x3ba8ba2f,0x33033444,0x34a5b913,0x3bcebbb6,0x3b0ebbf6,0x3b77b93a,0xb78b2e46,0x35c2ba0f,0x2a48b8c4,0x3bfaba8a,0xbbfe3a6d,0xacb5b89b,
0xbb3b381d,0x2fd6b9cb,0xb6d73add,0xbbf13984,0xb9ed3bea,0xbb993848,0x395fb0b2,0xb5053ac2,0x356433c6,0xb7e33b77,0x3b88bbc3,0x3af6b5c2,
0x323e3872,0xbb993ac2,0x3bd9baa7,0x35053848,0x3bd9baa7,0x37e335c2,0xb23eb872,0x3af6bb77,0xb23eb872,0x3a0fbbe2,0xbbd93aa7,0xb93ab179,
0xbbd93aa7,0xba4f2648,0x323e3872,0xb8ec3bff,0xb6d7b81d,0x3ac2baf6,0xbb3b3add,0xb848b7e3,0xb95f3bea,0xbb502cb5,0x39ed30b2,0xb67c3bfa,
0x3b88b3c6,0x31793a4f,0x3564bbc3,0x3be2b8ec,0xaa48ba6d,0x39cbbb99,0xbbfe38c4,0xb984b505,0x3913378b,0xb9843b25,0x3a2fbb0e,0x39cb3732,
0x2e46bba8,0x3bceb7e3,0xbbf634a5,0xb303baf6,0xba2f3b0e,0xbb77acb5,0x3913378b,0xb5c23bfa,0x3bf6b4a5,0x389b38ec,0x2e46bba8,0x3a8aba4f,
0xba6db6d7,0x37e3bb50,0xb8c43b3b,0xbaf6b67c,0x381d39ed,0xb93a3a8a,0x3addb95f,0x3a0f389b,0xb0b2bb88,0x3a4fb984,0xbbea3564,0xb8ecb9cb,
0xb3c63bfe,0xbb253848,0x3bc32a48,0x37323ac2,0x3b64361f,0xb4443b77,0x361fbb64,0x3bb635c2,0xbb64b61f,0x2cb5bbe2,0xb61f3b64,0xbbfab179,
0x3b64361f,0x2fd63bff,0x361fbb64,0x3bf1a648,0xbb64b61f,0xb505bbce,0xb61f3b64,0xbb993303,0xbbeab564,0x2648bb99,0xb0b23b88,0xbbffb505,
0x3bc3aa48,0x38483bb6,0xb3c6bbfe,0x3ac2b444,0xba6d36d7,0xbb50b93a,0x38c43b3b,0xb67c3a0f,0x381db9ed,0x3be22fd6,0xbaddb95f,0xb179bbf1,
0x3bf634a5,0x33033bb6,0xae46bba8,0x3bce3444,0xb913378b,0xbb77ba0f,0x3a2f3b0e,0xb5c2393a,0xae46bba8,0x3a8aafd6,0xbbf6b4a5,0xb89bbbf1,
0x3a2f3b0e,0x26483b25,0x3913b78b,0x3bff3732,0xbb88b3c6,0xb732bbce,0x35643bc3,0xbb25b303,0x2a48ba6d,0x3bb6367c,0xbbfeb8c4,0xb444bb50,
0x3b3b3add,0x2cb53a8a,0x36d7b81d,0x3bfa389b,0xb9ed30b2,0xbbf1b9cb,0x395f3bea,0xafd63984,0x3aa7323e,0x393a3be2,0xb872bbd9,0x3a0f3179,
0x38723bd9,0xb8ec2648,0x3aa7323e,0x3a4f3bff,0xbaa7b23e,0xbb25bbce,0x38723bd9,0xb7323303,0xb872bbd9,0x3444b67c,0xbaa7b23e,0xbbb6bb50,
0xb95fb0b2,0xba8abbf1,0x39ed3bea,0xb89bafd6,0xbb88bbc3,0x2648b732,0xb56433c6,0xbbffbb25,0xaa48b8c4,0x3ac237e3,0xbbfeba6d,0xb848baf6,
0x3b3b381d,0x3b503bfa,0xb6d7badd,0x367cacb5,0x378b2e46,0x3b773bfa,0xbb0ebbf6,0x35c22cb5,0x3ba83a2f,0x389b3a4f,0xb4a5b913,0x3a8a38ec,
0x3b0e3bf6,0x26483505,0x378b2e46,0x3bff3b99,0x34a53913,0xb848b444,0x3ba83a2f,0x3ac23bb6,0xb3c6aa48,0xbbf1bbff,0x3bc33bfe,0xafd6a648,
0xb8c4b6d7,0xbb99bbce,0x3a6d3b3b,0xb505b303,0xbaddb9ed,0xbaf6bb50,0x381d395f,0xb7e3b67c,0xbbeabb88,0xba0fba8a,0x30b23564,0xb93ab89b,
0x3c003c00,0xba4fb9cb,0,0xb8ecb984,0x3c003c00,0xbb25bac2,0,0xb732b848,0x3c003c00,0xbbb6bb77,0,0xb444b5c2,
0x3c003c00,0xbbfabbe2,0,0xacb5b179,0x33c62a48,0x367c393a,0x3bc33bfe,0xbb50ba0f,0x38c436d7,0xb1792fd6,0x3a6d3b3b,0xbbe2bbf1,
0x3add39ed,0xb984b732,0x381d395f,0xb9cbbb25,0x3bea3b88,0xbbcebaf6,0x30b23564,0xb303b7e3,0xbb0ebbf6,0x3be23a4f,0x378b2e46,0x317938ec,
0xb4a5b913,0x39843b99,0x3ba83a2f,0xb9cbb505,0x378b2e46,0xb3033444,0x3b0e3bf6,0xbbcebbb6,0x3ba83a2f,0xbb77b93a,0x34a53913,0xb5c2ba0f,
0xb95fb0b2,0x2cb5b89b,0xb9edbbea,0x3bfa3a8a,0xbb88bbc3,0x3bf13984,0x3564b3c6,0x2fd639cb,0xaa48b8c4,0x35053ac2,0x3bfe3a6d,0xbb99b848,
0x3b3b381d,0xbaf6b5c2,0x36d73add,0xb7e3bb77,0x38723bd9,0xbb99bac2,0xbaa7b23e,0x3505b848,0xbaa7b23e,0x37e3b5c2,0xb872bbd9,0x3af63b77,
0xb872bbd9,0x3a0f3be2,0x3aa7323e,0xb93a3179,0x3aa7323e,0xba4fa648,0x38723bd9,0xb8ecbbff,0x3b8833c6,0xb84837e3,0x35643bc3,0xbac2baf6,
0xaa483a6d,0xb67cbbfa,0xbbfeb8c4,0x3b502cb5,0xbb3bbadd,0x3be238ec,0x36d7b81d,0xb1793a4f,0x39edb0b2,0xb9843505,0x395f3bea,0xb9cbbb99,
0xae46bba8,0x39843b25,0x3bf634a5,0xb9cb3732,0x3a2f3b0e,0xbbceb7e3,0xb913378b,0x3303baf6,0xbbf6b4a5,0x3b77acb5,0xae46bba8,0x35c23bfa,
0x3913b78b,0xb89b38ec,0x3a2f3b0e,0xba8aba4f,0xbbeab564,0x3af6b67c,0x30b2bb88,0x37e33b50,0x3bc3aa48,0xba0f389b,0x33c63bfe,0xb93aba8a,
0xba6d36d7,0x38ecb9cb,0xb8c4bb3b,0x3a4f3984,0x381db9ed,0xb7323ac2,0x3add395f,0xbb25b848,0xb61f3b64,0xb444bb77,0xbb64b61f,0x3bb6b5c2,
0x361fbb64,0x2cb53be2,0x3b64361f,0xbbfa3179,0xb61f3b64,0x2fd6bbff,0xbb64b61f,0x3bf12648,0x361fbb64,0xb5053bce,0x3b64361f,0xbb99b303,
0x3a6d36d7,0xbbff3505,0xb8c43b3b,0xa648bb99,0xb81db9ed,0x3ac23444,0x3addb95f,0xb8483bb6,0x30b23b88,0xb67cba0f,0xbbea3564,0x3b50b93a,
0x33c6bbfe,0xb1793bf1,0x3bc32a48,0xbbe22fd6,0x3a2fbb0e,0xb3033bb6,0x3913378b,0xbbce3444,0xbbf634a5,0x3b77ba0f,0x2e46bba8,0x35c2393a,
0x3913378b,0xba8aafd6,0xba2f3b0e,0x389bbbf1,0x2e46bba8,0xa6483b25,0x3bf6b4a5,0xbbff3732,0xb6d7b81d,0x3b25b303,0x3b3bbadd,0xb7323bce,
0xb95f3bea,0x3444bb50,0xb9edb0b2,0x3bb6b67c,0x3b88b3c6,0xbbfa389b,0xb5643bc3,0x2cb5ba8a,0xaa48ba6d,0x2fd63984,0x3bfeb8c4,0xbbf139cb,
0xbbd93aa7,0x393abbe2,0xb23eb872,0x3a0fb179,0x323e3872,0xb8eca648,0xbbd93aa7,0x3a4fbbff,0x3bd9baa7,0xbb253bce,0x323e3872,0xb732b303,
0xb23eb872,0x3444367c,0x3bd9baa7,0xbbb63b50,0xaa4838c4,0xb89b2fd6,0xbbfe3a6d,0x3a8abbf1,0x3b3bb81d,0xbbff3b25,0xb6d73add,0xa648b732,
0x39edbbea,0xb8483af6,0x395fb0b2,0xbac237e3,0xb564b3c6,0x367c2cb5,0x3b88bbc3,0xbb503bfa,0x3ba8ba2f,0xbb773bfa,0xb4a53913,0xb5c22cb5,
0x3b0ebbf6,0xb89b3a4f,0x378bae46,0xba8a38ec,0x34a5b913,0xa6483505,0x3ba8ba2f,0xbbff3b99,0xb78b2e46,0x3848b444,0x3b0ebbf6,0xbac23bb6,
0x381db95f,0x2fd6a648,0x3addb9ed,0xbbf13bff,0x30b2b564,0x3505b303,0x3beabb88,0xbb993bce,0xb3c62a48,0x37e3b67c,0x3bc3bbfe,0xbaf63b50,
0xb8c436d7,0x393ab89b,0x3a6dbb3b,0xba0f3a8a,0xb9a839a8,0x3bf1bbff,0x39a8b9a8,0xafd62648,0xb9a839a8,0x3b99bbce,0x39a8b9a8,0xb5053303,
0xb9a839a8,0x3af6bb50,0x39a8b9a8,0xb7e3367c,0xb9a839a8,0x3a0fba8a,0x39a8b9a8,0xb93a389b,0xbadd39ed,0x35c2acb5,0xb81d395f,0x3b77bbfa,
0xbbea3b88,0x3a8ab8ec,0xb0b23564,0x389bba4f,0xbbc33bfe,0x3bffbb99,0x33c6aa48,0x2648b505,0xba6d3b3b,0x3ac2bbb6,0x38c4b6d7,0xb8483444,
0x34a5b913,0xba8a3bf1,0xbba83a2f,0x389bafd6,0xb78b2e46,0x26483732,0xbb0e3bf6,0x3bffbb25,0xbba83a2f,0x3ac2b7e3,0xb4a53913,0x3848baf6,
0xbb0e3bf6,0x3b50bbfa,0x378bae46,0xb67cacb5,0x3bfeba6d,0xba0f3179,0x2a48b8c4,0xb93a3be2,0x36d7badd,0xba4f3bff,0xbb3b381d,0x38ec2648,
0xb95f30b2,0x37323303,0xb9ed3bea,0x3b25bbce,0xbb883bc3,0x3bb6bb50,0x356433c6,0xb444b67c,0x323e3872,0x3732bbce,0x3bd9baa7,0xbb253303,
0x3bd9baa7,0xbbb6367c,0xb23eb872,0xb4443b50,0xb23eb872,0xacb53a8a,0xbbd93aa7,0x3bfab89b,0xbbd93aa7,0x3bf1b9cb,0x323e3872,0xafd6b984,
0xbb3b3add,0x3bceb444,0x36d7381d,0x3303bbb6,0x39ed30b2,0xb5c2b93a,0x395fbbea,0xbb773a0f,0x3564bbc3,0xb89b3bf1,0xbb8833c6,0x3a8a2fd6,
0xbbfe38c4,0x3bffb732,0x2a483a6d,0x2648bb25,0xb913b78b,0x26483b99,0xba2f3b0e,0x3bffb505,0xae463ba8,0x3848bbb6,0x3bf6b4a5,0xbac2b444,
0x3a2fbb0e,0xbb50393a,0xb913b78b,0x367c3a0f,0xbbf634a5,0x3be2afd6,0xae463ba8,0x3179bbf1,0x38c4bb3b,0xbbb635c2,0xba6db6d7,0x34443b77,
0xbadd395f,0x3bfab179,0x381d39ed,0xacb5bbe2,0x3beab564,0xbbf1a648,0xb0b2bb88,0xafd63bff,0xbbc3aa48,0x3b993303,0xb3c63bfe,0x3505bbce,
0x3b64361f,0xb7e3bb50,0x361fbb64,0xbaf6367c,0xbb64b61f,0x393a3a8a,0xb61f3b64,0x3a0fb89b,0x3b64361f,0xba4fb984,0x361fbb64,0xb8ec39cb,
0xbb64b61f,0x3b253848,0xb61f3b64,0x3732bac2,0xb0b23b88,0x39cbb732,0x3bea3564,0xb984bb25,0xb3c6bbfe,0xb3033af6,0xbbc32a48,0x3bce37e3,
0x38c43b3b,0xb5c2bbfa,0x3a6db6d7,0xbb772cb5,0xbaddb95f,0x3a8a3a4f,0xb81d39ed,0x389bb8ec,0xbbf6b4a5,0x3ac23af6,0x2e463ba8,0x3848b7e3,
0x3913b78b,0xbb50acb5,0xba2fbb0e,0x367c3bfa,0x2e463ba8,0x3179ba4f,0x3bf634a5,0xbbe2b8ec,0xba2fbb0e,0x39cb3b99,0xb913378b,0x3984b505,
0xb564bbc3,0xb5053848,0xbb88b3c6,0x3b993ac2,0x3bfe38c4,0xbaf6bb77,0x2a48ba6d,0xb7e335c2,0xb6d7381d,0x393ab179,0x3b3b3add,0xba0fbbe2,
0xb95fbbea,0x38ec3bff,0xb9ed30b2,0x3a4f2648,0x3aa7323e,0xbbfaba8a,0xb872bbd9,0xacb5389b,0x38723bd9,0xafd6b9cb,0x3aa7323e,0xbbf1b984,
0xbaa7b23e,0x3b993848,0x38723bd9,0xb505bac2,0xb872bbd9,0x37e33b77,0xbaa7b23e,0x3af635c2,0x39ed3bea,0xb179b8ec,0x395f30b2,0xbbe2ba4f,
0xb56433c6,0x39cb3505,0x3b883bc3,0xb984bb99,0xbbfeba6d,0x3bce3bb6,0x2a4838c4,0x3303b444,0xb6d7badd,0x35c23a0f,0xbb3bb81d,0x3b77393a,
0xb78bae46,0x3b503a0f,0x3b0e3bf6,0xb67cb93a,0xbba8ba2f,0x3be23bf1,0x34a53913,0x3179afd6,0xbb0ebbf6,0x39cb3b25,0xb78bae46,0x39843732,
0xb4a5b913,0x330337e3,0xbba8ba2f,0x3bce3af6,0xbbc3bbfe,0x38ec3984,0xb3c6aa48,0x3a4f39cb,0xba6dbb3b,0x37323848,0xb8c4b6d7,0x3b253ac2,
0xb81db95f,0x344435c2,0xbaddb9ed,0x3bb63b77,0xb0b2b564,0x2cb53179,0xbbeabb88,0x3bfa3be2,0x3c003c00,0x3a4f39cb,0,0x38ec3984,
0x3c003c00,0x3b253ac2,0,0x37323848,0x3c003c00,0x3bb63b77,0,0x344435c2,0x3c003c00,0x3bfa3be2,0,0x2cb53179,
0x33c62a48,0xb67cb93a,0x3bc33bfe,0x3b503a0f,0x38c436d7,0x3179afd6,0x3a6d3b3b,0x3be23bf1,0x3add39ed,0x39843732,0x381d395f,0x39cb3b25,
0x3bea3b88,0x3bce3af6,0x30b23564,0x330337e3,0xbb0ebbf6,0xbbe2ba4f,0x378b2e46,0xb179b8ec,0xb4a5b913,0xb984bb99,0x3ba83a2f,0x39cb3505,
0x378b2e46,0x3303b444,0x3b0e3bf6,0x3bce3bb6,0x3ba83a2f,0x3b77393a,0x34a53913,0x35c23a0f,0xb95fb0b2,0xacb5389b,0xb9edbbea,0xbbfaba8a,
0xbb88bbc3,0xbbf1b984,0x3564b3c6,0xafd6b9cb,0xaa48b8c4,0xb505bac2,0x3bfe3a6d,0x3b993848,0x3b3b381d,0x3af635c2,0x36d73add,0x37e33b77,
0x38723bd9,0x3b993ac2,0xbaa7b23e,0xb5053848,0xbaa7b23e,0xb7e335c2,0xb872bbd9,0xbaf6bb77,0xb872bbd9,0xba0fbbe2,0x3aa7323e,0x393ab179,
0x3aa7323e,0x3a4f2648,0x38723bd9,0x38ec3bff,0x3b8833c6,0x3848b7e3,0x35643bc3,0x3ac23af6,0xaa483a6d,0x367c3bfa,0xbbfeb8c4,0xbb50acb5,
0xbb3bbadd,0xbbe2b8ec,0x36d7b81d,0x3179ba4f,0x39edb0b2,0x3984b505,0x395f3bea,0x39cb3b99,0xae46bba8,0xb984bb25,0x3bf634a5,0x39cbb732,
0x3a2f3b0e,0x3bce37e3,0xb913378b,0xb3033af6,0xbbf6b4a5,0xbb772cb5,0xae46bba8,0xb5c2bbfa,0x3913b78b,0x389bb8ec,0x3a2f3b0e,0x3a8a3a4f,
0xbbeab564,0xbaf6367c,0x30b2bb88,0xb7e3bb50,0x3bc3aa48,0x3a0fb89b,0x33c63bfe,0x393a3a8a,0xba6d36d7,0xb8ec39cb,0xb8c4bb3b,0xba4fb984,
0x381db9ed,0x3732bac2,0x3add395f,0x3b253848,0xb61f3b64,0x34443b77,0xbb64b61f,0xbbb635c2,0x361fbb64,0xacb5bbe2,0x3b64361f,0x3bfab179,
0xb61f3b64,0xafd63bff,0xbb64b61f,0xbbf1a648,0x361fbb64,0x3505bbce,0x3b64361f,0x3b993303,0x3a6d36d7,0x3bffb505,0xb8c43b3b,0x26483b99,
0xb81db9ed,0xbac2b444,0x3addb95f,0x3848bbb6,0x30b23b88,0x367c3a0f,0xbbea3564,0xbb50393a,0x33c6bbfe,0x3179bbf1,0x3bc32a48,0x3be2afd6,
0x3a2fbb0e,0x3303bbb6,0x3913378b,0x3bceb444,0xbbf634a5,0xbb773a0f,0x2e46bba8,0xb5c2b93a,0x3913378b,0x3a8a2fd6,0xba2f3b0e,0xb89b3bf1,
0x2e46bba8,0x2648bb25,0x3bf6b4a5,0x3bffb732,0xb6d7b81d,0xbb253303,0x3b3bbadd,0x3732bbce,0xb95f3bea,0xb4443b50,0xb9edb0b2,0xbbb6367c,
0x3b88b3c6,0x3bfab89b,0xb5643bc3,0xacb53a8a,0xaa48ba6d,0xafd6b984,0x3bfeb8c4,0x3bf1b9cb,0xbbd93aa7,0xb93a3be2,0xb23eb872,0xba0f3179,
0x323e3872,0x38ec2648,0xbbd93aa7,0xba4f3bff,0x3bd9baa7,0x3b25bbce,0x323e3872,0x37323303,0xb23eb872,0xb444b67c,0x3bd9baa7,0x3bb6bb50,
0xaa4838c4,0x389bafd6,0xbbfe3a6d,0xba8a3bf1,0x3b3bb81d,0x3bffbb25,0xb6d73add,0x26483732,0x39edbbea,0x3848baf6,0x395fb0b2,0x3ac2b7e3,
0xb564b3c6,0xb67cacb5,0x3b88bbc3,0x3b50bbfa,0x3ba8ba2f,0x3b77bbfa,0xb4a53913,0x35c2acb5,0x3b0ebbf6,0x389bba4f,0x378bae46,0x3a8ab8ec,
0x34a5b913,0x2648b505,0x3ba8ba2f,0x3bffbb99,0xb78b2e46,0xb8483444,0x3b0ebbf6,0x3ac2bbb6,0x381db95f,0xafd62648,0x3addb9ed,0x3bf1bbff,
0x30b2b564,0xb5053303,0x3beabb88,0x3b99bbce,0xb3c62a48,0xb7e3367c,0x3bc3bbfe,0x3af6bb50,0xb8c436d7,0xb93a389b,0x3a6dbb3b,0x3a0fba8a,
0xb9a839a8,0xbbf13bff,0x39a8b9a8,0x2fd6a648,0xb9a839a8,0xbb993bce,0x39a8b9a8,0x3505b303,0xb9a839a8,0xbaf63b50,0x39a8b9a8,0x37e3b67c,
0xb9a839a8,0xba0f3a8a,0x39a8b9a8,0x393ab89b,0xbadd39ed,0xb5c22cb5,0xb81d395f,0xbb773bfa,0xbbea3b88,0xba8a38ec,0xb0b23564,0xb89b3a4f,
0xbbc33bfe,0xbbff3b99,0x33c6aa48,0xa6483505,0xba6d3b3b,0xbac23bb6,0x38c4b6d7,0x3848b444,0x34a5b913,0x3a8abbf1,0xbba83a2f,0xb89b2fd6,
0xb78b2e46,0xa648b732,0xbb0e3bf6,0xbbff3b25,0xbba83a2f,0xbac237e3,0xb4a53913,0xb8483af6,0xbb0e3bf6,0xbb503bfa,0x378bae46,0x367c2cb5,
0x3bfeba6d,0x3a0fb179,0x2a48b8c4,0x393abbe2,0x36d7badd,0x3a4fbbff,0xbb3b381d,0xb8eca648,0xb95f30b2,0xb732b303,0xb9ed3bea,0xbb253bce,
0xbb883bc3,0xbbb63b50,0x356433c6,0x3444367c,0x323e3872,0xb7323bce,0x3bd9baa7,0x3b25b303,0x3bd9baa7,0x3bb6b67c,0xb23eb872,0x3444bb50,
0xb23eb872,0x2cb5ba8a,0xbbd93aa7,0xbbfa389b,0xbbd93aa7,0xbbf139cb,0x323e3872,0x2fd63984,0xbb3b3add,0xbbce3444,0x36d7381d,0xb3033bb6,
0x39ed30b2,0x35c2393a,0x395fbbea,0x3b77ba0f,0x3564bbc3,0x389bbbf1,0xbb8833c6,0xba8aafd6,0xbbfe38c4,0xbbff3732,0x2a483a6d,0xa6483b25,
0xb913b78b,0xa648bb99,0xba2f3b0e,0xbbff3505,0xae463ba8,0xb8483bb6,0x3bf6b4a5,0x3ac23444,0x3a2fbb0e,0x3b50b93a,0xb913b78b,0xb67cba0f,
0xbbf634a5,0xbbe22fd6,0xae463ba8,0xb1793bf1,0x38c4bb3b,0x3bb6b5c2,0xba6db6d7,0xb444bb77,0xbadd395f,0xbbfa3179,0x381d39ed,0x2cb53be2,
0x3beab564,0x3bf12648,0xb0b2bb88,0x2fd6bbff,0xbbc3aa48,0xbb99b303,0xb3c63bfe,0xb5053bce,0x3b64361f,0x37e33b50,0x361fbb64,0x3af6b67c,
0xbb64b61f,0xb93aba8a,0xb61f3b64,0xba0f389b,0x3b64361f,0x3a4f3984,0x361fbb64,0x38ecb9cb,0xbb64b61f,0xbb25b848,0xb61f3b64,0xb7323ac2,
0xb0b23b88,0xb9cb3732,0x3bea3564,0x39843b25,0xb3c6bbfe,0x3303baf6,0xbbc32a48,0xbbceb7e3,0x38c43b3b,0x35c23bfa,0x3a6db6d7,0x3b77acb5,
0xbaddb95f,0xba8aba4f,0xb81d39ed,0xb89b38ec,0xbbf6b4a5,0xbac2baf6,0x2e463ba8,0xb84837e3,0x3913b78b,0x3b502cb5,0xba2fbb0e,0xb67cbbfa,
0x2e463ba8,0xb1793a4f,0x3bf634a5,0x3be238ec,0xba2fbb0e,0xb9cbbb99,0xb913378b,0xb9843505,0xb564bbc3,0x3505b848,0xbb88b3c6,0xbb99bac2,
0x3bfe38c4,0x3af63b77,0x2a48ba6d,0x37e3b5c2,0xb6d7381d,0xb93a3179,0x3b3b3add,0x3a0f3be2,0xb95fbbea,0xb8ecbbff,0xb9ed30b2,0xba4fa648,
0x3aa7323e,0x3bfa3a8a,0xb872bbd9,0x2cb5b89b,0x38723bd9,0x2fd639cb,0x3aa7323e,0x3bf13984,0xbaa7b23e,0xbb99b848,0x38723bd9,0x35053ac2,
0xb872bbd9,0xb7e3bb77,0xbaa7b23e,0xbaf6b5c2,0x39ed3bea,0x317938ec,0x395f30b2,0x3be23a4f,0xb56433c6,0xb9cbb505,0x3b883bc3,0x39843b99,
0xbbfeba6d,0xbbcebbb6,0x2a4838c4,0xb3033444,0xb6d7badd,0xb5c2ba0f,0xbb3bb81d,0xbb77b93a,0xb78bae46,0xbb50ba0f,0x3b0e3bf6,0x367c393a,
0xbba8ba2f,0xbbe2bbf1,0x34a53913,0xb1792fd6,0xbb0ebbf6,0xb9cbbb25,0xb78bae46,0xb984b732,0xb4a5b913,0xb303b7e3,0xbba8ba2f,0xbbcebaf6,
0xbbc3bbfe,0xb8ecb984,0xb3c6aa48,0xba4fb9cb,0xba6dbb3b,0xb732b848,0xb8c4b6d7,0xbb25bac2,0xb81db95f,0xb444b5c2,0xbaddb9ed,0xbbb6bb77,
0xb0b2b564,0xacb5b179,0xbbeabb88,0xbbfabbe2,0x3c003c00,0x96480000,0x3c003c00,0xa311a248,0x3c003c00,0x9cb69a48,0x3c003c00,0xa452a3db,
0x3c003c00,0x9fdb9e48,0x3c003c00,0xa51ba4b6,0x3c003c00,0xa17fa0b6,0x3bff3c00,0xa5e4a57f,0x3c003c00,0x9fdb0000,0x3bfb3bfc,0xac6aabd9,
0x3bff3c00,0xa5e4a3db,0x3bf93bfa,0xad65ace7,0x3bfe3bff,0xa8e8a7da,0x3bf63bf7,0xae5fade2,0x3bfd3bfe,0xaadea9e3,0x3bf23bf4,0xaf59aedc,
0x3c003c00,0xa3110000,0x3bf03bf4,0xafefaf0e,0x3bfe3bff,0xa94da711,0x3be83bed,0xb0d7b067,0x3bfb3bfd,0xac6aab11,0x3bdf3be4,0xb1b6b147,
0x3bf63bf9,0xae2dad4c,0x3bd43bda,0xb294b226,0x3c003c00,0xa51b0000,0x3bdf3be6,0xb1b6b115,0x3bfc3bfe,0xaba7a91b,0x3bcf3bd7,0xb2f7b257,
0x3bf63bf9,0xae5fad1a,0x3bbc3bc6,0xb41ab396,0x3bec3bf1,0xb074afa4,0x3ba53bb1,0xb4b7b469,0x3bff3c00,0xa6ad0000,0x3bc83bd4,0xb371b2a1,
0x3bfa3bfd,0xad00aaac,0x3bac3bbb,0xb487b420,0x3bef3bf5,0xb029aeaa,0x3b8b3b9d,0xb552b4ed,0x3bde3be7,0xb1cfb0fd,0x3b653b79,0xb61ab5b6,
0x3bff3c00,0xa81f0000,0x3bab3bbc,0xb493b414,0x3bf63bfc,0xae2dac1f,0x3b813b97,0xb58db511,0x3be53bef,0xb122b01d,0x3b4f3b69,0xb682b608,
0x3bcc3bda,0xb328b226,0x3b163b33,0xb76fb6f9,0x3bfe3c00,0xa8e80000,0x3b873ba0,0xb56ab4d5,0x3bf23bfa,0xaf59ace7,0x3b4c3b6b,0xb68db5fd,
0x3bda3be8,0xb219b0e4,0x3b073b2b,0xb7a6b71b,0x3bb73bca,0xb43eb34c,0x3ab63ae0,0xb85ab817,0x3bfe3c00,0xa9b10000,0x3b5e3b80,0xb63cb593,
0x3bee3bf8,0xb042adb0,0x3b103b39,0xb785b6e3,0x3bce3be0,0xb30fb1aa,0x3ab33ae3,0xb85fb812,0x3b9e3bb7,0xb4e7b438,0x3a493a7f,0xb8f3b8ab,
0x3bfd3c00,0xaa7a0000,0x3b2f3b5a,0xb70ab64e,0x3be83bf6,0xb0d7ae78,0x3acb3aff,0xb83ab7c2,0x3bbf3bd6,0xb402b26f,0x3a543a92,0xb8e5b891,
0x3b813ba2,0xb58db4c9,0x39cd3a13,0xb982b935,0x3bfd3c00,0xab430000,0x3afb3b30,0xb7d2b705,0x3be23bf3,0xb16caf40,0x3a7e3abf,0xb8adb84d,
0x3bae3bcb,0xb47bb334,0x39eb3a37,0xb962b909,0x3b603b8a,0xb631b558,0x3946399b,0xba04b9b5,0x3bfc3c00,0xac060000,0x3ac13b02,0xb84ab7b7,
0x3bdc3bf0,0xb201b004,0x3a293a78,0xb91bb8b5,0x3b9c3bc0,0xb4f3b3f7,0x397939d4,0xb9d6b97b,0x3b3d3b70,0xb6d2b5e5,0x38b23918,0xba7aba2b,
0x3bfb3c00,0xac6a0000,0x3a813ad0,0xb8a8b832,0x3bd43bed,0xb294b067,0x39cd3a2b,0xb982b918,0x3b873bb2,0xb56ab45d,0x38fd3969,0xba41b9e5,
0x3b163b53,0xb76fb670,0x3815388c,0xbae1ba95,0x3bfa3c00,0xacce0000,0x3a3d3a99,0xb902b887,0x3bcc3be9,0xb328b0cb,0x396b39d8,0xb9e3b976,
0x3b713ba4,0xb5dfb4bd,0x387a38f6,0xbaa2ba47,0x3aeb3b33,0xb805b6f9,0x36dd37ee,0xbb3abaf3,0x3bf93c00,0xad330000,0x39f43a5e,0xb958b8d8,
0x3bc33be5,0xb3bab12e,0x39023980,0xba3db9d0,0x3b593b95,0xb654b51d,0x37dd387c,0xbaf7baa0,0x3abd3b11,0xb850b780,0x358136b5,0xbb83bb43,
0x3bf83c00,0xad970000,0x39a63a1f,0xb9aab927,0x3bba3be1,0xb426b191,0x38943922,0xba90ba23,0x3b3f3b84,0xb6c6b57c,0x36bb37f9,0xbb42baf0,
0x3a8c3aed,0xb899b802,0x341a3570,0xbbbcbb86,0x3bf73c00,0xadfb0000,0x395439dc,0xb9f8b972,0x3bb03bdc,0xb46fb1f4,0x382038bf,0xbadbba71,
0x3b243b72,0xb737b5da,0x358d36ee,0xbb81bb36,0x3a583ac6,0xb8e0b842,0x31533420,0xbbe3bbbb,0x3bf63c00,0xae5f0000,0x38fd3996,0xba41b9ba,
0x3ba53bd7,0xb4b7b257,0x374e3858,0xbb1ebab8,0x3b073b5f,0xb7a6b637,0x345735da,0xbbb3bb72,0x3a213a9c,0xb924b881,0x2cce3191,0xbbfabbe1,
0x3bf53c00,0xaec30000,0x38a3394d,0xba85b9fe,0x3b9a3bd2,0xb4ffb2b9,0x365437d8,0xbb59baf9,0x3ae83b4b,0xb80ab693,0x323234bd,0xbbd9bba4,
0x39e73a71,0xb966b8bf,0xa4522db0,0xbc00bbf8,0x3bf33c00,0xaf270000,0x38453900,0xbac4ba3f,0x3b8e3bcd,0xb546b31b,0x355236f9,0xbb8bbb33,
0x3ac73b36,0xb840b6ee,0x2f593334,0xbbf2bbcb,0x39aa3a43,0xb9a6b8fb,0xaef51a48,0xbbf4bc00,0x3bf23c00,0xaf8b0000,0x37c838b0,0xbafeba7c,
0x3b813bc7,0xb58db37d,0x344b3614,0xbbb5bb67,0x3aa53b20,0xb874b748,0x288430e4,0xbbffbbe8,0x396b3a13,0xb9e3b935,0xb263ad4c,0xbbd7bbf9,
0x3bf03c00,0xafef0000,0x36ff385d,0xbb32bab5,0x3b733bc1,0xb5d4b3df,0x327c3529,0xbbd6bb93,0x3a813b08,0xb8a8b7a1,0xa9b12d1a,0xbbfebbf9,
0x392939e1,0xba1db96d,0xb49fb160,0xbba9bbe3,0x3bef3c00,0xb0290000,0x36313807,0xbb60bae9,0x3b653bbb,0xb61ab420,0x305b3438,0xbbedbbb7,
0x3a5c3af0,0xb8dbb7f9,0xafef1e48,0xbbf0bc00,0x38e539ad,0xba54b9a4,0xb602b408,0xbb6abbbe,0x3bed3c00,0xb05b0000,0x355e375e,0xbb89bb1a,
0x3b573bb4,0xb65fb451,0x2c6a3288,0xbbfbbbd5,0x3a353ad6,0xb90cb828,0xb27cac51,0xbbd6bbfb,0x389e3976,0xba89b9d8,0xb759b558,0xbb1bbb8a,
0x3beb3c00,0xb08d0000,0x348736aa,0xbbacbb46,0x3b473bad,0xb6a4b481,0x16483099,0xbc00bbeb,0x3a0d3abc,0xb93cb852,0xb47bb080,0xbbaebbec,
0x3855393e,0xbababa0b,0xb850b69e,0xbabdbb49,0x3be93c00,0xb0be0000,0x335935f1,0xbbc9bb6e,0x3b373ba6,0xb6e8b4b1,0xac382d4c,0xbbfcbbf9,
0x39e33aa0,0xb96bb87c,0xb5b1b2d2,0xbb7abbd1,0x380a3905,0xbae8ba3b,0xb8eab7d8,0xba50baf9,0x3be73c00,0xb0f00000,0x319e3534,0xbbe0bb91,
0x3b273b9e,0xb72cb4e1,0xb042257f,0xbbeebc00,0x39b83a83,0xb999b8a6,0xb6ddb48d,0xbb3abbab,0x377a38c9,0xbb13ba69,0xb979b881,0xb9d6ba9c,
0x3be53c00,0xb1220000,0x2fbd3475,0xbbf1bbaf,0x3b163b97,0xb76fb511,0xb263a91b,0xbbd7bbfe,0x398b3a65,0xb9c5b8ce,0xb7feb5ab,0xbaeebb7b,
0x36dd388c,0xbb3aba95,0xb9fcb90e,0xb94fba33,0x3be33c00,0xb1530000,0x2c383365,0xbbfcbbc9,0x3b043b8f,0xb7b2b540,0xb43eae78,0xbbb7bbf6,
0x395d3a47,0xb9f0b8f6,0xb889b6c1,0xba97bb41,0x363c384d,0xbb5ebabf,0xba73b992,0xb8bcb9be,0x3be13c00,0xb1850000,0x217f31db,0xbc00bbdd,
0x3af13b86,0xb7f3b570,0xb546b12e,0xbb8ebbe5,0x392e3a27,0xba19b91d,0xb90cb7cd,0xba35bafc,0x3599380d,0xbb7fbae6,0xbadbba0b,0xb820b93e,
0x3bdf3c00,0xb1b60000,0xa9b1304e,0xbbfebbed,0x3ade3b7d,0xb81ab59f,0xb648b31b,0xbb5cbbcd,0x38fd3a07,0xba41b943,0xb986b867,0xb9c9baae,
0x34f33796,0xbb9cbb0b,0xbb35ba78,0xb6f4b8b5,0x3bdd3c00,0xb1e80000,0xae5f2d7e,0xbbf6bbf8,0x3acb3b74,0xb83ab5ce,0xb742b481,0xbb21bbad,
0x38cc39e5,0xba67b969,0xb9f8b8e2,0xb954ba56,0x344b3710,0xbbb5bb2e,0xbb7fbad9,0xb599b822,0x3bda3c00,0xb2190000,0xb0f028b6,0xbbe7bbff,
0x3ab63b6b,0xb85ab5fd,0xb81ab570,0xbadebb86,0x389939c3,0xba8cb98d,0xba60b956,0xb8d6b9f6,0x33403687,0xbbcbbb4e,0xbbb8bb2e,0xb432b710,
0x3bff3bff,0xa6ada648,0x3bfe3bff,0xa8e8a8b6,0x3bff3bff,0xa776a711,0x3bfe3bfe,0xa94da91b,0x3bff3bff,0xa81fa7da,0x3bfe3bfe,0xa9b1a97f,
0x3bff3bff,0xa884a852,0x3bfe3bfe,0xaa16a9e3,0x3bef3bf1,0xb029afd6,0x3bda3bdd,0xb219b1db,0x3bea3bed,0xb0a6b067,0x3bd43bd7,0xb294b257,
0x3be53be8,0xb122b0e4,0x3bce3bd1,0xb30fb2d2,0x3be03be3,0xb19eb160,0x3bc63bca,0xb389b34c,0x3bc83bce,0xb371b303,0x3b873b91,0xb56ab534,
0x3bba3bc1,0xb426b3df,0x3b733b7d,0xb5d4b59f,0x3bab3bb2,0xb493b45d,0x3b5e3b69,0xb63cb608,0x3b9a3ba2,0xb4ffb4c9,0x3b473b53,0xb6a4b670,
0x3b8b3b99,0xb552b505,0x3b073b1a,0xb7a6b75e,0x3b6f3b7d,0xb5ebb59f,0x3ade3af3,0xb81ab7ee,0x3b4f3b5f,0xb682b637,0x3ab33ac9,0xb85fb83d,
0x3b2c3b3e,0xb715b6cc,0x3a853a9c,0xb8a3b881,0x3b3a3b50,0xb6ddb67c,0x3a5c3a7c,0xb8dbb8b0,0x3b0a3b22,0xb79bb73d,0x3a193a3b,0xb92eb905,
0x3ad53af0,0xb82ab7f9,0x39d239f6,0xb97db956,0x3a9b3ab8,0xb884b858,0x398639ad,0xb9c9b9a4,0x3ad53af6,0xb82ab7e3,0x398b39ba,0xb9c5b996,
0x3a8c3ab1,0xb899b862,0x3929395b,0xba1db9f2,0x3a3d3a65,0xb902b8ce,0x38c138f6,0xba6fba47,0x39e73a13,0xb966b935,0x3855388c,0xbababa95,
0x3a5c3a8a,0xb8dbb89b,0x389938d8,0xba8cba5e,0x39f83a2b,0xb954b918,0x38153858,0xbae1bab8,0x398b39c3,0xb9c5b98d,0x371537a1,0xbb2cbb08,
0x39163951,0xba2db9fa,0x35f73687,0xbb6cbb4e,0x39d23a0f,0xb97db93a,0x371537b7,0xbb2cbb02,0x394f3992,0xb9fcb9be,0x35c83670,0xbb76bb53,
0x38c13909,0xba6fba37,0x346f351d,0xbbb0bb95,0x382a3877,0xbad5baa3,0x3219337d,0xbbdabbc7,0x39373984,0xba11b9cb,0x34cf3593,0xbba1bb80,
0x389438e7,0xba90ba52,0x327c3408,0xbbd6bbbe,0x37c8383d,0xbafebac9,0x2e9130e4,0xbbf5bbe8,0x36543710,0xbb59bb2e,0x16482aac,0xbc00bbfd,
0x388e38ec,0xba93ba4f,0x30d732a1,0xbbe8bbd4,0x3790382d,0xbb0dbad3,0x28e82e14,0xbbfebbf7,0x35eb36c1,0xbb6fbb41,0xaccea4b6,0xbbfabc00,
0x34323511,0xbbb8bb97,0xb201b036,0xbbdcbbee,0x37b23848,0xbb04bac2,0x96482bd9,0xbc00bbfc,0x35df36cc,0xbb71bb3e,0xb010ac1f,0xbbefbbfc,
0x33eb34ed,0xbbc0bb9d,0xb402b20d,0xbbbfbbdb,0x2fef31f4,0xbbf0bbdc,0xb5ebb4f9,0xbb6fbb9b,0x36313732,0xbb60bb25,0xb0f0ad7e,0xbbe7bbf8,
0x341a3529,0xbbbcbb93,0xb49fb31b,0xbba9bbcd,0x2fbd320d,0xbbf1bbdb,0xb6afb5ab,0xbb45bb7b,0xa4522aac,0xbc00bbfd,0xb850b7ac,0xbabdbb05,
0x349f35c2,0xbba9bb77,0xb4dbb365,0xbb9fbbc9,0x308d32ea,0xbbebbbd0,0xb715b5fd,0xbb2cbb6b,0x9fdb2c51,0xbc00bbfb,0xb894b812,0xba90bae3,
0xb109ad4c,0xbbe6bbf9,0xb982b90e,0xb9cdba33,0x32013444,0xbbdcbbb6,0xb721b5f1,0xbb2abb6e,0x26ad2edc,0xbbffbbf4,0xb8adb822,0xba7ebad9,
0xb05bab11,0xbbedbbfd,0xb9aab930,0xb9a6ba17,0xb4b7b2ea,0xbba5bbd0,0xba81ba1b,0xb8a8b92b,0x2d653179,0xbbf9bbe2,0xb89eb807,0xba89bae9,
0xadc99a48,0xbbf8bc00,0xb9afb92b,0xb9a1ba1b,0xb432b1aa,0xbbb8bbe0,0xba93ba27,0xb88eb91d,0xb6d2b587,0xbb3dbb82,0xbb45baf3,0xb6afb7ee,
0xa51b2cb5,0xbc00bbfa,0xb990b900,0xb9c0ba3f,0xb294af40,0xbbd4bbf3,0xba89ba13,0xb89eb935,0xb625b4bd,0xbb63bba4,0xbb47baf0,0xb6a4b7f9,
0xb865b780,0xbab0bb11,0xbbc5bb8f,0xb3a2b540,0xafefa648,0xbbf0bbff,0xba60b9dc,0xb8d6b972,0xb517b31b,0xbb96bbcd,0xbb35bad3,0xb6f4b82d,
0xb7feb693,0xbaeebb4b,0xbbc0bb84,0xb3ebb57c,0xb94ab8ab,0xba00ba7f,0xbbfdbbe9,0xaa7ab0cb,0xb340afd6,0xbbcbbbf1,0xbb0aba99,0xb79bb887,
0xb6d2b540,0xbb3dbb8f,0xbbaebb67,0xb47bb614,0xb8dbb828,0xba5cbad6,0xbbfbbbe0,0xac9cb1aa,0xba15b980,0xb933b9d0,0xbbecbbff,0x30742852,
0xb53ab303,0xbb90bbce,0xbb89bb30,0xb55eb705,0xb83ab6e3,0xbacbbb39,0xbbf2bbca,0xaf8bb34c,0xb9a1b8f6,0xb9afba47,0xbbf5bc00,0x2ec39e48,
0xbac1ba3b,0xb84ab905,0xbb92bbd0,0x352f32ea,0xb6c6b505,0xbb3fbb99,0xbbdcbba0,0xb201b4d5,0xb8fdb838,0xba41bacc,0xbbfebbfb,0x2a16ac83,
0xba50b9b1,0xb8eab99f,0xbbaebbe4,0x347b3147,0xbb4abad9,0xb699b822,0xbaf1bb5d,0x37f33642,0xb820b67c,0xbadbbb50,0xbbffbbe6,0xa884b115,
0xb9afb8f1,0xb9a1ba4b,0xbbd2bbf8,0x32c62db0,0xbae5ba56,0xb80fb8e2,0xbb2abb8c,0x3721354c,0xbbaebb58,0xb47bb659,0xba11baaa,0x3937386d,
0xb8d1b7e3,0xba64baf6,0xbbf2bc00,0x2f8ba248,0xba4db99b,0xb8eeb9b5,0xbb6fbbc1,0x35eb33df,0xbb5cbae3,0xb648b812,0xba6bbafc,0x38c737cd,
0xbbebbbb4,0xb08db451,0xb8f8b9be,0x3a453992,0xb974b89b,0xb9daba8a,0xbbb5bbed,0x344b304e,0xbad5ba33,0xb82ab90e,0xbad8bb58,0x38253659,
0xbbb3bb55,0xb457b665,0xb979ba37,0x39d63909,0xbc00bbed,0x9648b067,0xb764b8a0,0x3b183a87,0xba09b93a,0xb941ba0f,0xbb4abbaf,0x36993475,
0xbb45bab8,0xb6afb858,0xba11babf,0x3937384d,0xbbeabbab,0xb0a6b48d,0xb85ab943,0x3ab63a07,0xbbecbc00,0x30749a48,0xb493b6b5,0x3bab3b43,
0xba8cb9cb,0xb899b984,0xbab3bb46,0x385f36aa,0xbb9cbb28,0xb4f3b726,0xb91fb9fa,0x3a253951,0xbc00bbe4,0xa452b147,0xb631b828,0x3b603ad6,
0xbbb0bbee,0x346f3036,0xae5fb3df,0x3bf63bc1,0xbafeba4f,0xb7c8b8ec,0xb9f4bab5,0x3958385d,0xbbd8bb82,0xb24bb587,0xb80ab90e,0x3ae83a33,
0xbbf3bbfe,0x2f27a97f,0xb2f7b5da,0x3bcf3b72,0xbb4cbbb7,0x368d3438,0x2dc9ac1f,0x3bf83bfc,0xbb5cbac2,0xb648b848,0xb911b9fe,0x3a31394d,
0xbbf9bbc4,0xad33b3ae,0xb5b1b802,0x3b7a3aed,0xbbc5bbf9,0x33a22d1a,0xa94db26f,0x3bfe3bd6,0xbac4bb5d,0x38453642,0x346f2fa4,0x3bb03bf1,
0xbba5bb25,0xb4b7b732,0xb80fb927,0x3ae53a1f,0xbbffbbee,0x2884b036,0xb24bb5b6,0x3bd83b79,0xbb76bbd6,0x35c8326f,0x305ba7da,0x3bed3bff,
0xba19bae0,0x392e3817,0x374234c9,0x3b213ba2,0xbbd9bb77,0xb232b5c2,0xb5ebb832,0x3b6f3ad0,0xbbe8bc00,0x30d7a57f,0xa81fb288,0x3bff3bd5,
0xbb07bb95,0x37a6351d,0x34f33080,0x3b9c3bec,0xb94fba43,0x39fc38fb,0x38ea3780,0x3a503b11,0xbbf8bbb6,0xadc9b444,0xb328b64e,0x3bcc3b5a,
0xbbb7bbf8,0x343e2db0,0x3042a9e3,0x3bee3bfe,0xba7abb36,0x38b236ee,0x379034ed,0x3b0d3b9d,0xb86ab989,0x3aac39c7,0x3a0438fb,0x39463a43,
0xbc00bbe2,0x2311b179,0xac9cb414,0x3bfb3bbc,0xbb6abbd7,0x36023257,0x34b72f40,0x3ba53bf3,0xb9d2babc,0x397d3852,0x38f83775,0x3a453b14,
0xb6ddb8b5,0x3b3a3a78,0x3ae83a0b,0x380a393e,0xbbf2bbfa,0x2f8bacb5,0x2d33af0e,0x3bf93bf4,0xbb04bb9e,0x37b234e1,0x372c3451,0x3b273bb4,
0xb911ba27,0x3a31391d,0x3a0038e2,0x394a3a56,0xb4c3b796,0x3ba33b0b,0x3b8b3ae6,0x3552380d,0x3c003c00,0x16480000,0x3c003c00,0x1cb61a48,
0x3c003c00,0x1fdb1e48,0x3c003c00,0x217f20b6,0x3c003c00,0x23112248,0x3c003c00,0x245223db,0x3c003c00,0x251b24b6,0x3bff3c00,0x25e4257f,
0x3c003c00,0x1fdb0000,0x3bff3c00,0x25e423db,0x3bfe3bff,0x28e827da,0x3bfd3bfe,0x2ade29e3,0x3bfb3bfc,0x2c6a2bd9,0x3bf93bfa,0x2d652ce7,
0x3bf63bf7,0x2e5f2de2,0x3bf23bf4,0x2f592edc,0x3c003c00,0x23110000,0x3bfe3bff,0x294d2711,0x3bfb3bfd,0x2c6a2b11,0x3bf63bf9,0x2e2d2d4c,
0x3bf03bf4,0x2fef2f0e,0x3be83bed,0x30d73067,0x3bdf3be4,0x31b63147,0x3bd43bda,0x32943226,0x3c003c00,0x251b0000,0x3bfc3bfe,0x2ba7291b,
0x3bf63bf9,0x2e5f2d1a,0x3bec3bf1,0x30742fa4,0x3bdf3be6,0x31b63115,0x3bcf3bd7,0x32f73257,0x3bbc3bc6,0x341a3396,0x3ba53bb1,0x34b73469,
0x3bff3c00,0x26ad0000,0x3bfa3bfd,0x2d002aac,0x3bef3bf5,0x30292eaa,0x3bde3be7,0x31cf30fd,0x3bc83bd4,0x337132a1,0x3bac3bbb,0x34873420,
0x3b8b3b9d,0x355234ed,0x3b653b79,0x361a35b6,0x3bff3c00,0x281f0000,0x3bf63bfc,0x2e2d2c1f,0x3be53bef,0x3122301d,0x3bcc3bda,0x33283226,
0x3bab3bbc,0x34933414,0x3b813b97,0x358d3511,0x3b4f3b69,0x36823608,0x3b163b33,0x376f36f9,0x3bfe3c00,0x28e80000,0x3bf23bfa,0x2f592ce7,
0x3bda3be8,0x321930e4,0x3bb73bca,0x343e334c,0x3b873ba0,0x356a34d5,0x3b4c3b6b,0x368d35fd,0x3b073b2b,0x37a6371b,0x3ab63ae0,0x385a3817,
0x3bfe3c00,0x29b10000,0x3bee3bf8,0x30422db0,0x3bce3be0,0x330f31aa,0x3b9e3bb7,0x34e73438,0x3b5e3b80,0x363c3593,0x3b103b39,0x378536e3,
0x3ab33ae3,0x385f3812,0x3a493a7f,0x38f338ab,0x3bfd3c00,0x2a7a0000,0x3be83bf6,0x30d72e78,0x3bbf3bd6,0x3402326f,0x3b813ba2,0x358d34c9,
0x3b2f3b5a,0x370a364e,0x3acb3aff,0x383a37c2,0x3a543a92,0x38e53891,0x39cd3a13,0x39823935,0x3bfd3c00,0x2b430000,0x3be23bf3,0x316c2f40,
0x3bae3bcb,0x347b3334,0x3b603b8a,0x36313558,0x3afb3b30,0x37d23705,0x3a7e3abf,0x38ad384d,0x39eb3a37,0x39623909,0x3946399b,0x3a0439b5,
0x3bfc3c00,0x2c060000,0x3bdc3bf0,0x32013004,0x3b9c3bc0,0x34f333f7,0x3b3d3b70,0x36d235e5,0x3ac13b02,0x384a37b7,0x3a293a78,0x391b38b5,
0x397939d4,0x39d6397b,0x38b23918,0x3a7a3a2b,0x3bfb3c00,0x2c6a0000,0x3bd43bed,0x32943067,0x3b873bb2,0x356a345d,0x3b163b53,0x376f3670,
0x3a813ad0,0x38a83832,0x39cd3a2b,0x39823918,0x38fd3969,0x3a4139e5,0x3815388c,0x3ae13a95,0x3bfa3c00,0x2cce0000,0x3bcc3be9,0x332830cb,
0x3b713ba4,0x35df34bd,0x3aeb3b33,0x380536f9,0x3a3d3a99,0x39023887,0x396b39d8,0x39e33976,0x387a38f6,0x3aa23a47,0x36dd37ee,0x3b3a3af3,
0x3bf93c00,0x2d330000,0x3bc33be5,0x33ba312e,0x3b593b95,0x3654351d,0x3abd3b11,0x38503780,0x39f43a5e,0x395838d8,0x39023980,0x3a3d39d0,
0x37dd387c,0x3af73aa0,0x358136b5,0x3b833b43,0x3bf83c00,0x2d970000,0x3bba3be1,0x34263191,0x3b3f3b84,0x36c6357c,0x3a8c3aed,0x38993802,
0x39a63a1f,0x39aa3927,0x38943922,0x3a903a23,0x36bb37f9,0x3b423af0,0x341a3570,0x3bbc3b86,0x3bf73c00,0x2dfb0000,0x3bb03bdc,0x346f31f4,
0x3b243b72,0x373735da,0x3a583ac6,0x38e03842,0x395439dc,0x39f83972,0x382038bf,0x3adb3a71,0x358d36ee,0x3b813b36,0x31533420,0x3be33bbb,
0x3bf63c00,0x2e5f0000,0x3ba53bd7,0x34b73257,0x3b073b5f,0x37a63637,0x3a213a9c,0x39243881,0x38fd3996,0x3a4139ba,0x374e3858,0x3b1e3ab8,
0x345735da,0x3bb33b72,0x2cce3191,0x3bfa3be1,0x3bf53c00,0x2ec30000,0x3b9a3bd2,0x34ff32b9,0x3ae83b4b,0x380a3693,0x39e73a71,0x396638bf,
0x38a3394d,0x3a8539fe,0x365437d8,0x3b593af9,0x323234bd,0x3bd93ba4,0xa4522db0,0x3c003bf8,0x3bf33c00,0x2f270000,0x3b8e3bcd,0x3546331b,
0x3ac73b36,0x384036ee,0x39aa3a43,0x39a638fb,0x38453900,0x3ac43a3f,0x355236f9,0x3b8b3b33,0x2f593334,0x3bf23bcb,0xaef51a48,0x3bf43c00,
0x3bf23c00,0x2f8b0000,0x3b813bc7,0x358d337d,0x3aa53b20,0x38743748,0x396b3a13,0x39e33935,0x37c838b0,0x3afe3a7c,0x344b3614,0x3bb53b67,
0x288430e4,0x3bff3be8,0xb263ad4c,0x3bd73bf9,0x3bf03c00,0x2fef0000,0x3b733bc1,0x35d433df,0x3a813b08,0x38a837a1,0x392939e1,0x3a1d396d,
0x36ff385d,0x3b323ab5,0x327c3529,0x3bd63b93,0xa9b12d1a,0x3bfe3bf9,0xb49fb160,0x3ba93be3,0x3bef3c00,0x30290000,0x3b653bbb,0x361a3420,
0x3a5c3af0,0x38db37f9,0x38e539ad,0x3a5439a4,0x36313807,0x3b603ae9,0x305b3438,0x3bed3bb7,0xafef1e48,0x3bf03c00,0xb602b408,0x3b6a3bbe,
0x3bed3c00,0x305b0000,0x3b573bb4,0x365f3451,0x3a353ad6,0x390c3828,0x389e3976,0x3a8939d8,0x355e375e,0x3b893b1a,0x2c6a3288,0x3bfb3bd5,
0xb27cac51,0x3bd63bfb,0xb759b558,0x3b1b3b8a,0x3beb3c00,0x308d0000,0x3b473bad,0x36a43481,0x3a0d3abc,0x393c3852,0x3855393e,0x3aba3a0b,
0x348736aa,0x3bac3b46,0x16483099,0x3c003beb,0xb47bb080,0x3bae3bec,0xb850b69e,0x3abd3b49,0x3be93c00,0x30be0000,0x3b373ba6,0x36e834b1,
0x39e33aa0,0x396b387c,0x380a3905,0x3ae83a3b,0x335935f1,0x3bc93b6e,0xac382d4c,0x3bfc3bf9,0xb5b1b2d2,0x3b7a3bd1,0xb8eab7d8,0x3a503af9,
0x3be73c00,0x30f00000,0x3b273b9e,0x372c34e1,0x39b83a83,0x399938a6,0x377a38c9,0x3b133a69,0x319e3534,0x3be03b91,0xb042257f,0x3bee3c00,
0xb6ddb48d,0x3b3a3bab,0xb979b881,0x39d63a9c,0x3be53c00,0x31220000,0x3b163b97,0x376f3511,0x398b3a65,0x39c538ce,0x36dd388c,0x3b3a3a95,
0x2fbd3475,0x3bf13baf,0xb263a91b,0x3bd73bfe,0xb7feb5ab,0x3aee3b7b,0xb9fcb90e,0x394f3a33,0x3be33c00,0x31530000,0x3b043b8f,0x37b23540,
0x395d3a47,0x39f038f6,0x363c384d,0x3b5e3abf,0x2c383365,0x3bfc3bc9,0xb43eae78,0x3bb73bf6,0xb889b6c1,0x3a973b41,0xba73b992,0x38bc39be,
0x3be13c00,0x31850000,0x3af13b86,0x37f33570,0x392e3a27,0x3a19391d,0x3599380d,0x3b7f3ae6,0x217f31db,0x3c003bdd,0xb546b12e,0x3b8e3be5,
0xb90cb7cd,0x3a353afc,0xbadbba0b,0x3820393e,0x3bdf3c00,0x31b60000,0x3ade3b7d,0x381a359f,0x38fd3a07,0x3a413943,0x34f33796,0x3b9c3b0b,
0xa9b1304e,0x3bfe3bed,0xb648b31b,0x3b5c3bcd,0xb986b867,0x39c93aae,0xbb35ba78,0x36f438b5,0x3bdd3c00,0x31e80000,0x3acb3b74,0x383a35ce,
0x38cc39e5,0x3a673969,0x344b3710,0x3bb53b2e,0xae5f2d7e,0x3bf63bf8,0xb742b481,0x3b213bad,0xb9f8b8e2,0x39543a56,0xbb7fbad9,0x35993822,
0x3bda3c00,0x32190000,0x3ab63b6b,0x385a35fd,0x389939c3,0x3a8c398d,0x33403687,0x3bcb3b4e,0xb0f028b6,0x3be73bff,0xb81ab570,0x3ade3b86,
0xba60b956,0x38d639f6,0xbbb8bb2e,0x34323710,0x3bd83c00,0x324b0000,0x3aa23b62,0x387a362b,0x3865399f,0x3ab039b1,0x31e835fd,0x3bdd3b6b,
0xb2ada248,0x3bd33c00,0xb88eb659,0x3a933b58,0xbabdb9c3,0x3850398d,0xbbe1bb74,0x318535ce,0x3bd63c00,0x327c0000,0x3a8c3b58,0x38993659,
0x3830397b,0x3ad139d4,0x308d3570,0x3beb3b86,0xb432abd9,0x3bb83bfc,0xb8fdb73d,0x3a413b22,0xbb10ba27,0x3785391d,0xbbf9bbad,0x2d333481,
0x3bd33c00,0x32ad0000,0x3a763b4e,0x38b73687,0x37f33956,0x3af139f6,0x2e5f34e1,0x3bf63b9e,0xb50baf0e,0x3b983bf4,0xb966b80d,0x39e73ae6,
0xbb57ba83,0x365f38a6,0xbc00bbd7,0xa17f3257,0x3bd03c00,0x32de0000,0x3a603b43,0x38d636b5,0x37853930,0x3b103a17,0x2b433451,0x3bfd3bb4,
0xb5dfb115,0x3b713be6,0xb9c9b877,0x39863aa3,0xbb92bad6,0x352f3828,0xbbf5bbf3,0xae912f40,0x3bce3c00,0x330f0000,0x3a493b39,0x38f336e3,
0x37153909,0x3b2c3a37,0x2311337d,0x3c003bc7,0xb6afb2a1,0x3b453bd4,0xba25b8dd,0x391f3a5a,0xbbc0bb20,0x33eb3748,0xbbd9bbff,0xb2322711,
0x3bcb3c00,0x33400000,0x3a313b2e,0x39113710,0x36a438e2,0x3b473a56,0xa7763257,0x3bff3bd7,0xb77ab414,0x3b133bbc,0xba7ab93e,0x38b23a0b,
0xbbe2bb5f,0x316c3637,0xbbacbbfd,0xb487ab75,0x3bc83c00,0x33710000,0x3a193b22,0x392e373d,0x363138ba,0x3b603a74,0xac9c312e,0x3bfb3be5,
0xb820b4d5,0x3adb3ba0,0xbac7b99b,0x384039b5,0xbbf8bb95,0x2dc9351d,0xbb6fbbeb,0xb5ebb099,0x3bc53c00,0x33a20000,0x3a003b17,0x394a376a,
0x35bc3891,0x3b783a92,0xaf593004,0x3bf23bf0,0xb87fb593,0x3a9e3b80,0xbb0db9f2,0x3790395b,0xbc00bbc0,0x217f33f7,0xbb21bbca,0xb742b34c,
0x3bc23c00,0x33d30000,0x39e73b0b,0x39663796,0x35463867,0x3b8e3aae,0xb1092db0,0x3be63bf8,0xb8dbb64e,0x3a5c3b5a,0xbb4aba43,0x369938fb,
0xbbfbbbe0,0xac6a31aa,0xbac4bb9b,0xb845b4f9,0x3bbf3c00,0x34020000,0x39cd3aff,0x398237c2,0x34cf383d,0x3ba13ac9,0xb2632aac,0x3bd73bfd,
0xb933b705,0x3a153b30,0xbb7fba8e,0x35993896,0xbbe9bbf5,0xb0be2eaa,0xba58bb5d,0xb8e0b642,0x3bbc3c00,0x341a0000,0x39b33af3,0x399d37ee,
0x34573812,0x3bb33ae3,0xb3ba23db,0x3bc33c00,0xb986b7b7,0x39c93b02,0xbbabbad3,0x3493382d,0xbbcbbbff,0xb34027da,0xb9dfbb11,0xb970b780,
0x3bb83c00,0x34320000,0x39993ae6,0x39b8380d,0x33ba37cd,0x3bc33afc,0xb487a57f,0x3bac3c00,0xb9d6b832,0x39793ad0,0xbbcebb11,0x330f3780,
0xbb9fbbfe,0xb4dba97f,0xb958bab8,0xb9f4b858,0x3bb53c00,0x344b0000,0x397d3ad9,0x39d23822,0x32c63775,0x3bd23b14,0xb52fab75,0x3b923bfd,
0xba21b887,0x39243a99,0xbbe7bb49,0x30f0369e,0xbb68bbf2,0xb60eaf72,0xb8c7ba52,0xba6bb8e7,0x3bb23c00,0x34630000,0x39623acc,0x39eb3838,
0x31cf371b,0x3bde3b2b,0xb5d4ae14,0x3b733bf7,0xba67b8d8,0x38cc3a5e,0xbbf8bb79,0x2d9735b6,0xbb24bbdb,0xb737b20d,0xb82ab9e1,0xbad5b96d,
0x3bae3c00,0x347b0000,0x39463abf,0x3a04384d,0x30d736c1,0x3be83b41,0xb676b036,0x3b523bee,0xbaa9b927,0x386f3a1f,0xbc00bba2,0x251b34c9,
0xbad5bbb9,0xb82ab42c,0xb70ab964,0xbb2fb9e9,0x3bab3c00,0x34930000,0x39293ab1,0x3a1d3862,0x2fbd3665,0x3bf13b55,0xb715b160,0x3b2c3be3,
0xbae5b972,0x380f39dc,0xbbfebbc4,0xaa1633ae,0xba7abb8c,0xb8b2b54c,0xb5b1b8dd,0xbb7aba5a,0x3ba73c00,0x34ab0000,0x390c3aa3,0x3a353877,
0x2dc93608,0x3bf83b69,0xb7b2b288,0x3b043bd5,0xbb1bb9ba,0x37593996,0xbbf2bbdf,0xaf5931c3,0xba15bb55,0xb933b665,0xb44bb84d,0xbbb5babf,
0x3ba33c00,0x34c30000,0x38ee3a95,0x3a4d388c,0x2ba735ab,0x3bfc3b7b,0xb825b3ae,0x3ad83bc4,0xbb4cb9fe,0x368d394d,0xbbdebbf1,0xb1cf2fa4,
0xb9a6bb14,0xb9aab775,0xb1b6b76a,0xbbdfbb17,0x3b9f3c00,0x34db0000,0x38d13a87,0x3a6438a0,0x2776354c,0x3bff3b8c,0xb86fb469,0x3aa93bb1,
0xbb78ba3f,0x35bc3900,0xbbc0bbfd,0xb3eb2b75,0xb92ebac9,0xba19b83d,0xad97b62b,0xbbf8bb62,0x3b9c3c00,0x34f30000,0x38b23a78,0x3a7a38b5,
0x964834ed,0x3c003b9d,0xb8b7b4f9,0x3a763b9b,0xbb9eba7c,0x34e738b0,0xbb9abc00,0xb4ff9a48,0xb8adba74,0xba7eb8ba,0x1cb6b4e1,0xbc00bb9e,
0x3b983c00,0x350b0000,0x38943a69,0x3a9038c9,0xa81f348d,0x3bff3bab,0xb8fdb587,0x3a413b82,0xbbbdbab5,0x340e385d,0xbb6abbfc,0xb602ac1f,
0xb825ba17,0xbad8b930,0x2e2db31b,0xbbf6bbcd,0x3b943c00,0x35230000,0x38743a5a,0x3aa538dd,0xac06342c,0x3bfc3bb9,0xb941b614,0x3a093b67,
0xbbd7bae9,0x32633807,0xbb32bbf0,0xb6ffb004,0xb72cb9b1,0xbb27b99f,0x3201b067,0xbbdcbbed,0x3b903c00,0x353a0000,0x38553a4b,0x3aba38f1,
0xadfb3396,0x3bf73bc6,0xb982b69e,0x39cd3b49,0xbbeabb1a,0x30a6375e,0xbaf1bbdc,0xb7f3b1f4,0xb602b943,0xbb6aba07,0x346faaac,0xbbb0bbfd,
0x3b8b3c00,0x35520000,0x38353a3b,0x3ace3905,0xafef32d2,0x3bf03bd1,0xb9c0b726,0x39903b28,0xbbf8bb46,0x2dc936aa,0xbaa9bbc1,0xb86fb3df,
0xb4cfb8ce,0xbba1ba65,0x35d42852,0xbb73bbff,0x3b873c00,0x356a0000,0x38153a2b,0x3ae13918,0xb0f0320d,0x3be73bdb,0xb9fcb7ac,0x394f3b05,
0xbbffbb6e,0x288435f1,0xba58bb9e,0xb8e0b4e1,0xb328b852,0xbbccbabc,0x372c2fa4,0xbb27bbf1,0x3b833c00,0x35810000,0x37e83a1b,0x3af4392b,
0xb1e83147,0x3bdd3be4,0xba35b817,0x390c3ae0,0xbc00bb91,0xa51b3534,0xba00bb74,0xb94ab5ce,0xb0a6b7a1,0xbbeabb08,0x383a3288,0xbacbbbd5,
0x3b7f3c00,0x35990000,0x37a63a0b,0x3b07393e,0xb2de3080,0x3bd03bec,0xba6bb858,0x38c73ab8,0xbbfabbaf,0xacce3475,0xb9a1bb43,0xb9afb6b5,
0xac38b693,0xbbfcbb4b,0x38d63499,0xba60bbaa,0x3b7a3c00,0x35b10000,0x376439fa,0x3b183951,0xb3d32f72,0x3bc23bf2,0xba9eb896,0x387f3a8e,
0xbbefbbc9,0xb0293365,0xb93cbb0b,0xba0db796,0x2311b57c,0xbc00bb84,0x396635e5,0xb9e7bb70,0x3b763c00,0x35c80000,0x372139e9,0x3b2a3964,
0xb4632de2,0x3bb23bf7,0xbaceb8d3,0x38353a62,0xbbddbbdd,0xb1e831db,0xb8d1bacc,0xba64b838,0x2dfbb45d,0xbbf7bbb2,0x39eb3726,0xb962bb28,
0x3b713c00,0x35df0000,0x36dd39d8,0x3b3a3976,0xb4db2c51,0x3b9f3bfb,0xbafbb90e,0x37d23a33,0xbbc5bbed,0xb3a2304e,0xb85fba87,0xbab3b8a0,
0x3185b26f,0xbbe1bbd6,0x3a64382d,0xb8d1bad3,0x3b6c3c00,0x35f70000,0x369939c7,0x3b4a3989,0xb552297f,0x3b8b3bfe,0xbb24b948,0x37373a02,
0xbba7bbf8,0xb4ab2d7e,0xb7d2ba3b,0xbafbb905,0x3402b01d,0xbbbfbbef,0x3ace38bf,0xb835ba71,0x3b683c00,0x360e0000,0x365439b5,0x3b59399b,
0xb5c824b6,0x3b763c00,0xbb4ab980,0x369939d0,0xbb83bbff,0xb58128b6,0xb6ddb9e9,0xbb3ab964,0x353aab11,0xbb90bbfd,0x3b2a3948,0xb721ba02,
0x2c002c00,0x2c002c00,0x2c002c00,0x2c002c00,0x2b642c00,0x261f29a8,0xa61f0000,0xab64a9a8,0x29a82c00,0xa9a80000,0xa9a8ac00,0x29a80000,
0x261f2c00,0xab64a9a8,0x2b640000,0xa61f29a8,0x2c00,0xac00,0x2c00,0xac00,0xa61f2c00,0x2b64a9a8,0xab640000,0x261f29a8,
0xa9a82c00,0x29a80000,0x29a8ac00,0xa9a80000,0xab642c00,0xa61f29a8,0x261f0000,0x2b64a9a8,0,0,0,0,
0x261f0000,0x2b6429a8,0x2b642c00,0x261f29a8,0x29a80000,0x29a82c00,0xa9a80000,0xa9a8ac00,0x2b640000,0xa61f29a8,0xa61fac00,0x2b6429a8,
0x2c000000,0xac000000,0x2c000000,0xac000000,0x2b640000,0xa61fa9a8,0xa61f2c00,0x2b64a9a8,0x29a80000,0x29a8ac00,0xa9a80000,0xa9a82c00,
0x261f0000,0x2b64a9a8,0x2b64ac00,0x261fa9a8,0xac002c00,0xac002c00,0xac002c00,0xac002c00,0xab642c00,0xa61f29a8,0x261f0000,0x2b64a9a8,
0xa9a82c00,0x29a80000,0x29a8ac00,0xa9a80000,0xa61f2c00,0x2b64a9a8,0xab640000,0x261f29a8,0x2c00,0xac00,0x2c00,0xac00,
0x261f2c00,0xab64a9a8,0x2b640000,0xa61f29a8,0x29a82c00,0xa9a80000,0xa9a8ac00,0x29a80000,0x2b642c00,0x261f29a8,0xa61f0000,0xab64a9a8,
0,0,0,0,0xa61f0000,0xab6429a8,0xab642c00,0xa61f29a8,0xa9a80000,0xa9a82c00,0x29a80000,0x29a8ac00,
0xab640000,0x261f29a8,0x261fac00,0xab6429a8,0xac000000,0x2c000000,0xac000000,0x2c000000,0xab640000,0x261fa9a8,0x261f2c00,0xab64a9a8,
0xa9a80000,0xa9a8ac00,0x29a80000,0x29a82c00,0xa61f0000,0xab64a9a8,0xab64ac00,0xa61fa9a8,0,0,0,0,
0xa61f0000,0xab64a9a8,0xab64ac00,0xa61fa9a8,0xa9a80000,0xa9a8ac00,0x29a80000,0x29a82c00,0xab640000,0x261fa9a8,0x261f2c00,0xab64a9a8,
0xac000000,0x2c000000,0xac000000,0x2c000000,0xab640000,0x261f29a8,0x261fac00,0xab6429a8,0xa9a80000,0xa9a82c00,0x29a80000,0x29a8ac00,
0xa61f0000,0xab6429a8,0xab642c00,0xa61f29a8,0x2c002c00,0x2c002c00,0x2c002c00,0x2c002c00,0x2b642c00,0x261f29a8,0xa61f0000,0xab64a9a8,
0x29a82c00,0xa9a80000,0xa9a8ac00,0x29a80000,0x261f2c00,0xab64a9a8,0x2b640000,0xa61f29a8,0x2c00,0xac00,0x2c00,0xac00,
0xa61f2c00,0x2b64a9a8,0xab640000,0x261f29a8,0xa9a82c00,0x29a80000,0x29a8ac00,0xa9a80000,0xab642c00,0xa61f29a8,0x261f0000,0x2b64a9a8,
0,0,0,0,0x261f0000,0x2b64a9a8,0x2b64ac00,0x261fa9a8,0x29a80000,0x29a8ac00,0xa9a80000,0xa9a82c00,
0x2b640000,0xa61fa9a8,0xa61f2c00,0x2b64a9a8,0x2c000000,0xac000000,0x2c000000,0xac000000,0x2b640000,0xa61f29a8,0xa61fac00,0x2b6429a8,
0x29a80000,0x29a82c00,0xa9a80000,0xa9a8ac00,0x261f0000,0x2b6429a8,0x2b642c00,0x261f29a8,0xac002c00,0xac002c00,0xac002c00,0xac002c00,
0xab642c00,0xa61f29a8,0x261f0000,0x2b64a9a8,0xa9a82c00,0x29a80000,0x29a8ac00,0xa9a80000,0xa61f2c00,0x2b64a9a8,0xab640000,0x261f29a8,
0x2c00,0xac00,0x2c00,0xac00,0x261f2c00,0xab64a9a8,0x2b640000,0xa61f29a8,0x29a82c00,0xa9a80000,0xa9a8ac00,0x29a80000,
0x2b642c00,0x261f29a8,0xa61f0000,0xab64a9a8,0x2c002c00,0x2c002c00,0x2c002c00,0x2c002c00,0xab64ac00,0xa61fa9a8,0x261f0000,0x2b6429a8,
0x29a82c00,0xa9a80000,0xa9a8ac00,0x29a80000,0xa61fac00,0x2b6429a8,0xab640000,0x261fa9a8,0x2c00,0xac00,0x2c00,0xac00,
0x261fac00,0xab6429a8,0x2b640000,0xa61fa9a8,0xa9a82c00,0x29a80000,0x29a8ac00,0xa9a80000,0x2b64ac00,0x261fa9a8,0xa61f0000,0xab6429a8,
0,0,0,0,0xa61f0000,0xab64a9a8,0xab64ac00,0xa61fa9a8,0x29a80000,0x29a82c00,0xa9a80000,0xa9a8ac00,
0xab640000,0x261fa9a8,0x261f2c00,0xab64a9a8,0x2c000000,0xac000000,0x2c000000,0xac000000,0xab640000,0x261f29a8,0x261fac00,0xab6429a8,
0x29a80000,0x29a8ac00,0xa9a80000,0xa9a82c00,0xa61f0000,0xab6429a8,0xab642c00,0xa61f29a8,0xac002c00,0xac002c00,0xac002c00,0xac002c00,
0x2b64ac00,0x261fa9a8,0xa61f0000,0xab6429a8,0xa9a82c00,0x29a80000,0x29a8ac00,0xa9a80000,0x261fac00,0xab6429a8,0x2b640000,0xa61fa9a8,
0x2c00,0xac00,0x2c00,0xac00,0xa61fac00,0x2b6429a8,0xab640000,0x261fa9a8,0x29a82c00,0xa9a80000,0xa9a8ac00,0x29a80000,
0xab64ac00,0xa61fa9a8,0x261f0000,0x2b6429a8,0,0,0,0,0x261f0000,0x2b64a9a8,0x2b64ac00,0x261fa9a8,
0xa9a80000,0xa9a82c00,0x29a80000,0x29a8ac00,0x2b640000,0xa61fa9a8,0xa61f2c00,0x2b64a9a8,0xac000000,0x2c000000,0xac000000,0x2c000000,
0x2b640000,0xa61f29a8,0xa61fac00,0x2b6429a8,0xa9a80000,0xa9a8ac00,0x29a80000,0x29a82c00,0x261f0000,0x2b6429a8,0x2b642c00,0x261f29a8,
0,0,0,0,0x261f0000,0x2b6429a8,0x2b642c00,0x261f29a8,0xa9a80000,0xa9a8ac00,0x29a80000,0x29a82c00,
0x2b640000,0xa61f29a8,0xa61fac00,0x2b6429a8,0xac000000,0x2c000000,0xac000000,0x2c000000,0x2b640000,0xa61fa9a8,0xa61f2c00,0x2b64a9a8,
0xa9a80000,0xa9a82c00,0x29a80000,0x29a8ac00,0x261f0000,0x2b64a9a8,0x2b64ac00,0x261fa9a8,0x2c002c00,0x2c002c00,0x2c002c00,0x2c002c00,
0xab64ac00,0xa61fa9a8,0x261f0000,0x2b6429a8,0x29a82c00,0xa9a80000,0xa9a8ac00,0x29a80000,0xa61fac00,0x2b6429a8,0xab640000,0x261fa9a8,
0x2c00,0xac00,0x2c00,0xac00,0x261fac00,0xab6429a8,0x2b640000,0xa61fa9a8,0xa9a82c00,0x29a80000,0x29a8ac00,0xa9a80000,
0x2b64ac00,0x261fa9a8,0xa61f0000,0xab6429a8,0,0,0,0,0xa61f0000,0xab6429a8,0xab642c00,0xa61f29a8,
0x29a80000,0x29a8ac00,0xa9a80000,0xa9a82c00,0xab640000,0x261f29a8,0x261fac00,0xab6429a8,0x2c000000,0xac000000,0x2c000000,0xac000000,
0xab640000,0x261fa9a8,0x261f2c00,0xab64a9a8,0x29a80000,0x29a82c00,0xa9a80000,0xa9a8ac00,0xa61f0000,0xab64a9a8,0xab64ac00,0xa61fa9a8,
0xac002c00,0xac002c00,0xac002c00,0xac002c00,0x2b64ac00,0x261fa9a8,0xa61f0000,0xab6429a8,0xa9a82c00,0x29a80000,0x29a8ac00,0xa9a80000,
0x261fac00,0xab6429a8,0x2b640000,0xa61fa9a8,0x2c00,0xac00,0x2c00,0xac00,0xa61fac00,0x2b6429a8,0xab640000,0x261fa9a8,
0x29a82c00,0xa9a80000,0xa9a8ac00,0x29a80000,0xab64ac00,0xa61fa9a8,0x261f0000,0x2b6429a8,0x2bd92c00,0x2aa72b64,0x287229a8,0x223e261f,
0x2aa72c00,0xa23e261f,0xabd9a9a8,0xa872ab64,0x28722c00,0xabd9a61f,0x223ea9a8,0x2aa72b64,0x223e2c00,0xa872ab64,0x2aa729a8,0xabd9a61f,
0xa23e2c00,0x2872ab64,0xaaa729a8,0x2bd9a61f,0xa8722c00,0x2bd9a61f,0xa23ea9a8,0xaaa72b64,0xaaa72c00,0x223e261f,0x2bd9a9a8,0x2872ab64,
0xabd92c00,0xaaa72b64,0xa87229a8,0xa23e261f,0x223e0000,0x2872261f,0x2aa729a8,0x2bd92b64,0x28720000,0x2bd92b64,0x223e29a8,0xaaa7a61f,
0x2aa70000,0x223e2b64,0xabd9a9a8,0x2872a61f,0x2bd90000,0xaaa7261f,0x2872a9a8,0xa23e2b64,0x2bd90000,0xaaa7a61f,0x287229a8,0xa23eab64,
0x2aa70000,0x223eab64,0xabd929a8,0x2872261f,0x28720000,0x2bd9ab64,0x223ea9a8,0xaaa7261f,0x223e0000,0x2872a61f,0x2aa7a9a8,0x2bd9ab64,
0xabd92c00,0xaaa72b64,0xa87229a8,0xa23e261f,0xaaa72c00,0x223e261f,0x2bd9a9a8,0x2872ab64,0xa8722c00,0x2bd9a61f,0xa23ea9a8,0xaaa72b64,
0xa23e2c00,0x2872ab64,0xaaa729a8,0x2bd9a61f,0x223e2c00,0xa872ab64,0x2aa729a8,0xabd9a61f,0x28722c00,0xabd9a61f,0x223ea9a8,0x2aa72b64,
0x2aa72c00,0xa23e261f,0xabd9a9a8,0xa872ab64,0x2bd92c00,0x2aa72b64,0x287229a8,0x223e261f,0xa23e0000,0xa872261f,0xaaa729a8,0xabd92b64,
0xa8720000,0xabd92b64,0xa23e29a8,0x2aa7a61f,0xaaa70000,0xa23e2b64,0x2bd9a9a8,0xa872a61f,0xabd90000,0x2aa7261f,0xa872a9a8,0x223e2b64,
0xabd90000,0x2aa7a61f,0xa87229a8,0x223eab64,0xaaa70000,0xa23eab64,0x2bd929a8,0xa872261f,0xa8720000,0xabd9ab64,0xa23ea9a8,0x2aa7261f,
0xa23e0000,0xa872a61f,0xaaa7a9a8,0xabd9ab64,0xa23e0000,0xa872a61f,0xaaa7a9a8,0xabd9ab64,0xa8720000,0xabd9ab64,0xa23ea9a8,0x2aa7261f,
0xaaa70000,0xa23eab64,0x2bd929a8,0xa872261f,0xabd90000,0x2aa7a61f,0xa87229a8,0x223eab64,0xabd90000,0x2aa7261f,0xa872a9a8,0x223e2b64,
0xaaa70000,0xa23e2b64,0x2bd9a9a8,0xa872a61f,0xa8720000,0xabd92b64,0xa23e29a8,0x2aa7a61f,0xa23e0000,0xa872261f,0xaaa729a8,0xabd92b64,
0x2bd92c00,0x2aa72b64,0x287229a8,0x223e261f,0x2aa72c00,0xa23e261f,0xabd9a9a8,0xa872ab64,0x28722c00,0xabd9a61f,0x223ea9a8,0x2aa72b64,
0x223e2c00,0xa872ab64,0x2aa729a8,0xabd9a61f,0xa23e2c00,0x2872ab64,0xaaa729a8,0x2bd9a61f,0xa8722c00,0x2bd9a61f,0xa23ea9a8,0xaaa72b64,
0xaaa72c00,0x223e261f,0x2bd9a9a8,0x2872ab64,0xabd92c00,0xaaa72b64,0xa87229a8,0xa23e261f,0x223e0000,0x2872a61f,0x2aa7a9a8,0x2bd9ab64,
0x28720000,0x2bd9ab64,0x223ea9a8,0xaaa7261f,0x2aa70000,0x223eab64,0xabd929a8,0x2872261f,0x2bd90000,0xaaa7a61f,0x287229a8,0xa23eab64,
0x2bd90000,0xaaa7261f,0x2872a9a8,0xa23e2b64,0x2aa70000,0x223e2b64,0xabd9a9a8,0x2872a61f,0x28720000,0x2bd92b64,0x223e29a8,0xaaa7a61f,
0x223e0000,0x2872261f,0x2aa729a8,0x2bd92b64,0xabd92c00,0xaaa72b64,0xa87229a8,0xa23e261f,0xaaa72c00,0x223e261f,0x2bd9a9a8,0x2872ab64,
0xa8722c00,0x2bd9a61f,0xa23ea9a8,0xaaa72b64,0xa23e2c00,0x2872ab64,0xaaa729a8,0x2bd9a61f,0x223e2c00,0xa872ab64,0x2aa729a8,0xabd9a61f,
0x28722c00,0xabd9a61f,0x223ea9a8,0x2aa72b64,0x2aa72c00,0xa23e261f,0xabd9a9a8,0xa872ab64,0x2bd92c00,0x2aa72b64,0x287229a8,0x223e261f,
0xa23e0000,0xa872a61f,0xaaa7a9a8,0xabd9ab64,0x28720000,0x2bd92b64,0x223e29a8,0xaaa7a61f,0xaaa70000,0xa23eab64,0x2bd929a8,0xa872261f,
0x2bd90000,0xaaa7261f,0x2872a9a8,0xa23e2b64,0xabd90000,0x2aa7261f,0xa872a9a8,0x223e2b64,0x2aa70000,0x223eab64,0xabd929a8,0x2872261f,
0xa8720000,0xabd92b64,0xa23e29a8,0x2aa7a61f,0x223e0000,0x2872a61f,0x2aa7a9a8,0x2bd9ab64,0x2bd92c00,0x2aa72b64,0x287229a8,0x223e261f,
0xaaa7ac00,0x223ea61f,0x2bd929a8,0x28722b64,0x28722c00,0xabd9a61f,0x223ea9a8,0x2aa72b64,0xa23eac00,0x28722b64,0xaaa7a9a8,0x2bd9261f,
0xa23e2c00,0x2872ab64,0xaaa729a8,0x2bd9a61f,0x2872ac00,0xabd9261f,0x223e29a8,0x2aa7ab64,0xaaa72c00,0x223e261f,0x2bd9a9a8,0x2872ab64,
0x2bd9ac00,0x2aa7ab64,0x2872a9a8,0x223ea61f,0x223e0000,0x2872a61f,0x2aa7a9a8,0x2bd9ab64,0xa8720000,0xabd92b64,0xa23e29a8,0x2aa7a61f,
0x2aa70000,0x223eab64,0xabd929a8,0x2872261f,0xabd90000,0x2aa7261f,0xa872a9a8,0x223e2b64,0x2bd90000,0xaaa7261f,0x2872a9a8,0xa23e2b64,
0xaaa70000,0xa23eab64,0x2bd929a8,0xa872261f,0x28720000,0x2bd92b64,0x223e29a8,0xaaa7a61f,0xa23e0000,0xa872a61f,0xaaa7a9a8,0xabd9ab64,
0xabd92c00,0xaaa72b64,0xa87229a8,0xa23e261f,0x2aa7ac00,0xa23ea61f,0xabd929a8,0xa8722b64,0xa8722c00,0x2bd9a61f,0xa23ea9a8,0xaaa72b64,
0x223eac00,0xa8722b64,0x2aa7a9a8,0xabd9261f,0x223e2c00,0xa872ab64,0x2aa729a8,0xabd9a61f,0xa872ac00,0x2bd9261f,0xa23e29a8,0xaaa7ab64,
0x2aa72c00,0xa23e261f,0xabd9a9a8,0xa872ab64,0xabd9ac00,0xaaa7ab64,0xa872a9a8,0xa23ea61f,0xabd9ac00,0xaaa7ab64,0xa872a9a8,0xa23ea61f,
0x2aa72c00,0xa23e261f,0xabd9a9a8,0xa872ab64,0xa872ac00,0x2bd9261f,0xa23e29a8,0xaaa7ab64,0x223e2c00,0xa872ab64,0x2aa729a8,0xabd9a61f,
0x223eac00,0xa8722b64,0x2aa7a9a8,0xabd9261f,0xa8722c00,0x2bd9a61f,0xa23ea9a8,0xaaa72b64,0x2aa7ac00,0xa23ea61f,0xabd929a8,0xa8722b64,
0xabd92c00,0xaaa72b64,0xa87229a8,0xa23e261f,0xa23e0000,0xa872a61f,0xaaa7a9a8,0xabd9ab64,0x28720000,0x2bd92b64,0x223e29a8,0xaaa7a61f,
0xaaa70000,0xa23eab64,0x2bd929a8,0xa872261f,0x2bd90000,0xaaa7261f,0x2872a9a8,0xa23e2b64,0xabd90000,0x2aa7261f,0xa872a9a8,0x223e2b64,
0x2aa70000,0x223eab64,0xabd929a8,0x2872261f,0xa8720000,0xabd92b64,0xa23e29a8,0x2aa7a61f,0x223e0000,0x2872a61f,0x2aa7a9a8,0x2bd9ab64,
0x2bd9ac00,0x2aa7ab64,0x2872a9a8,0x223ea61f,0xaaa72c00,0x223e261f,0x2bd9a9a8,0x2872ab64,0x2872ac00,0xabd9261f,0x223e29a8,0x2aa7ab64,
0xa23e2c00,0x2872ab64,0xaaa729a8,0x2bd9a61f,0xa23eac00,0x28722b64,0xaaa7a9a8,0x2bd9261f,0x28722c00,0xabd9a61f,0x223ea9a8,0x2aa72b64,
0xaaa7ac00,0x223ea61f,0x2bd929a8,0x28722b64,0x2bd92c00,0x2aa72b64,0x287229a8,0x223e261f,0x223e0000,0x2872a61f,0x2aa7a9a8,0x2bd9ab64,
0xa8720000,0xabd92b64,0xa23e29a8,0x2aa7a61f,0x2aa70000,0x223eab64,0xabd929a8,0x2872261f,0xabd90000,0x2aa7261f,0xa872a9a8,0x223e2b64,
0x2bd90000,0xaaa7261f,0x2872a9a8,0xa23e2b64,0xaaa70000,0xa23eab64,0x2bd929a8,0xa872261f,0x28720000,0x2bd92b64,0x223e29a8,0xaaa7a61f,
0xa23e0000,0xa872a61f,0xaaa7a9a8,0xabd9ab64,0x3c003c00,0x3c003c00,0x3c003c00,0x3c003c00,0x3b643c00,0x361f39a8,0xb61f0000,0xbb64b9a8,
0x3c00,0xbc00,0x3c00,0xbc00,0xb61f3c00,0x3b64b9a8,0xbb640000,0x361f39a8,0xbc003c00,0xbc003c00,0xbc003c00,0xbc003c00,
0xbb643c00,0xb61f39a8,0x361f0000,0x3b64b9a8,0x3c00,0xbc00,0x3c00,0xbc00,0x361f3c00,0xbb64b9a8,0x3b640000,0xb61f39a8,
0,0,0,0,0xb61f0000,0xbb64b9a8,0xbb64bc00,0xb61fb9a8,0xbc000000,0x3c000000,0xbc000000,0x3c000000,
0xbb640000,0x361f39a8,0x361fbc00,0xbb6439a8,0,0,0,0,0x361f0000,0x3b64b9a8,0x3b64bc00,0x361fb9a8,
0x3c000000,0xbc000000,0x3c000000,0xbc000000,0x3b640000,0xb61f39a8,0xb61fbc00,0x3b6439a8,0x39a83c00,0xb9a80000,0xb9a8bc00,0x39a80000,
0x361f3c00,0xbb64b9a8,0x3b640000,0xb61f39a8,0xb9a83c00,0x39a80000,0x39a8bc00,0xb9a80000,0xbb643c00,0xb61f39a8,0x361f0000,0x3b64b9a8,
0xb9a83c00,0x39a80000,0x39a8bc00,0xb9a80000,0xb61f3c00,0x3b64b9a8,0xbb640000,0x361f39a8,0x39a83c00,0xb9a80000,0xb9a8bc00,0x39a80000,
0x3b643c00,0x361f39a8,0xb61f0000,0xbb64b9a8,0xb9a80000,0xb9a8bc00,0x39a80000,0x39a83c00,0xbb640000,0x361fb9a8,0x361f3c00,0xbb64b9a8,
0xb9a80000,0xb9a83c00,0x39a80000,0x39a8bc00,0xb61f0000,0xbb6439a8,0xbb643c00,0xb61f39a8,0x39a80000,0x39a8bc00,0xb9a80000,0xb9a83c00,
0x3b640000,0xb61fb9a8,0xb61f3c00,0x3b64b9a8,0x39a80000,0x39a83c00,0xb9a80000,0xb9a8bc00,0x361f0000,0x3b6439a8,0x3b643c00,0x361f39a8,
0,0,0,0,0x361f0000,0x3b6439a8,0x3b643c00,0x361f39a8,0x3c000000,0xbc000000,0x3c000000,0xbc000000,
0x3b640000,0xb61fb9a8,0xb61f3c00,0x3b64b9a8,0,0,0,0,0xb61f0000,0xbb6439a8,0xbb643c00,0xb61f39a8,
0xbc000000,0x3c000000,0xbc000000,0x3c000000,0xbb640000,0x361fb9a8,0x361f3c00,0xbb64b9a8,0x3c003c00,0x3c003c00,0x3c003c00,0x3c003c00,
0x3b643c00,0x361f39a8,0xb61f0000,0xbb64b9a8,0x3c00,0xbc00,0x3c00,0xbc00,0xb61f3c00,0x3b64b9a8,0xbb640000,0x361f39a8,
0xbc003c00,0xbc003c00,0xbc003c00,0xbc003c00,0xbb643c00,0xb61f39a8,0x361f0000,0x3b64b9a8,0x3c00,0xbc00,0x3c00,0xbc00,
0x361f3c00,0xbb64b9a8,0x3b640000,0xb61f39a8,0x39a80000,0x39a83c00,0xb9a80000,0xb9a8bc00,0x3b640000,0xb61f39a8,0xb61fbc00,0x3b6439a8,
0x39a80000,0x39a8bc00,0xb9a80000,0xb9a83c00,0x361f0000,0x3b64b9a8,0x3b64bc00,0x361fb9a8,0xb9a80000,0xb9a83c00,0x39a80000,0x39a8bc00,
0xbb640000,0x361f39a8,0x361fbc00,0xbb6439a8,0xb9a80000,0xb9a8bc00,0x39a80000,0x39a83c00,0xb61f0000,0xbb64b9a8,0xbb64bc00,0xb61fb9a8,
0x39a83c00,0xb9a80000,0xb9a8bc00,0x39a80000,0x361f3c00,0xbb64b9a8,0x3b640000,0xb61f39a8,0xb9a83c00,0x39a80000,0x39a8bc00,0xb9a80000,
0xbb643c00,0xb61f39a8,0x361f0000,0x3b64b9a8,0xb9a83c00,0x39a80000,0x39a8bc00,0xb9a80000,0xb61f3c00,0x3b64b9a8,0xbb640000,0x361f39a8,
0x39a83c00,0xb9a80000,0xb9a8bc00,0x39a80000,0x3b643c00,0x361f39a8,0xb61f0000,0xbb64b9a8,0x3c003c00,0x3c003c00,0x3c003c00,0x3c003c00,
0xbb64bc00,0xb61fb9a8,0x361f0000,0x3b6439a8,0x3c00,0xbc00,0x3c00,0xbc00,0x361fbc00,0xbb6439a8,0x3b640000,0xb61fb9a8,
0xbc003c00,0xbc003c00,0xbc003c00,0xbc003c00,0x3b64bc00,0x361fb9a8,0xb61f0000,0xbb6439a8,0x3c00,0xbc00,0x3c00,0xbc00,
0xb61fbc00,0x3b6439a8,0xbb640000,0x361fb9a8,0,0,0,0,0x361f0000,0x3b6439a8,0x3b643c00,0x361f39a8,
0xbc000000,0x3c000000,0xbc000000,0x3c000000,0x3b640000,0xb61fb9a8,0xb61f3c00,0x3b64b9a8,0,0,0,0,
0xb61f0000,0xbb6439a8,0xbb643c00,0xb61f39a8,0x3c000000,0xbc000000,0x3c000000,0xbc000000,0xbb640000,0x361fb9a8,0x361f3c00,0xbb64b9a8,
0x39a83c00,0xb9a80000,0xb9a8bc00,0x39a80000,0xb61fbc00,0x3b6439a8,0xbb640000,0x361fb9a8,0xb9a83c00,0x39a80000,0x39a8bc00,0xb9a80000,
0x3b64bc00,0x361fb9a8,0xb61f0000,0xbb6439a8,0xb9a83c00,0x39a80000,0x39a8bc00,0xb9a80000,0x361fbc00,0xbb6439a8,0x3b640000,0xb61fb9a8,
0x39a83c00,0xb9a80000,0xb9a8bc00,0x39a80000,0xbb64bc00,0xb61fb9a8,0x361f0000,0x3b6439a8,0xb9a80000,0xb9a8bc00,0x39a80000,0x39a83c00,
0x3b640000,0xb61f39a8,0xb61fbc00,0x3b6439a8,0xb9a80000,0xb9a83c00,0x39a80000,0x39a8bc00,0x361f0000,0x3b64b9a8,0x3b64bc00,0x361fb9a8,
0x39a80000,0x39a8bc00,0xb9a80000,0xb9a83c00,0xbb640000,0x361f39a8,0x361fbc00,0xbb6439a8,0x39a80000,0x39a83c00,0xb9a80000,0xb9a8bc00,
0xb61f0000,0xbb64b9a8,0xbb64bc00,0xb61fb9a8,0,0,0,0,0xb61f0000,0xbb64b9a8,0xbb64bc00,0xb61fb9a8,
0x3c000000,0xbc000000,0x3c000000,0xbc000000,0xbb640000,0x361f39a8,0x361fbc00,0xbb6439a8,0,0,0,0,
0x361f0000,0x3b64b9a8,0x3b64bc00,0x361fb9a8,0xbc000000,0x3c000000,0xbc000000,0x3c000000,0x3b640000,0xb61f39a8,0xb61fbc00,0x3b6439a8,
0x3c003c00,0x3c003c00,0x3c003c00,0x3c003c00,0xbb64bc00,0xb61fb9a8,0x361f0000,0x3b6439a8,0x3c00,0xbc00,0x3c00,0xbc00,
0x361fbc00,0xbb6439a8,0x3b640000,0xb61fb9a8,0xbc003c00,0xbc003c00,0xbc003c00,0xbc003c00,0x3b64bc00,0x361fb9a8,0xb61f0000,0xbb6439a8,
0x3c00,0xbc00,0x3c00,0xbc00,0xb61fbc00,0x3b6439a8,0xbb640000,0x361fb9a8,0x39a80000,0x39a83c00,0xb9a80000,0xb9a8bc00,
0xbb640000,0x361fb9a8,0x361f3c00,0xbb64b9a8,0x39a80000,0x39a8bc00,0xb9a80000,0xb9a83c00,0xb61f0000,0xbb6439a8,0xbb643c00,0xb61f39a8,
0xb9a80000,0xb9a83c00,0x39a80000,0x39a8bc00,0x3b640000,0xb61fb9a8,0xb61f3c00,0x3b64b9a8,0xb9a80000,0xb9a8bc00,0x39a80000,0x39a83c00,
0x361f0000,0x3b6439a8,0x3b643c00,0x361f39a8,0x39a83c00,0xb9a80000,0xb9a8bc00,0x39a80000,0xb61fbc00,0x3b6439a8,0xbb640000,0x361fb9a8,
0xb9a83c00,0x39a80000,0x39a8bc00,0xb9a80000,0x3b64bc00,0x361fb9a8,0xb61f0000,0xbb6439a8,0xb9a83c00,0x39a80000,0x39a8bc00,0xb9a80000,
0x361fbc00,0xbb6439a8,0x3b640000,0xb61fb9a8,0x39a83c00,0xb9a80000,0xb9a8bc00,0x39a80000,0xbb64bc00,0xb61fb9a8,0x361f0000,0x3b6439a8,
0x27fe2800,0x96480000,0x273b2764,0xa2d7a21f,0x27ea27f6,0x9cb29a46,0x26dd270e,0xa41da38b,0x27c327d9,0x9fc69e3e,0x266d26a7,0xa4c4a472,
0x278827a8,0xa164a0a5,0x25ed262f,0xa55fa513,0x27c32800,0x9fc60000,0xa4c4a21f,0xa66da764,0x25ed270e,0xa55fa38b,0xa73ba62f,0xa2d7a513,
0x21642472,0xa788a6a7,0xa7fea7d9,0x16489e3e,0x9cb21a46,0xa7eaa7f6,0xa6dda7a8,0x241d20a5,0x273b2800,0xa2d70000,0xa55fa764,0x25ed221f,
0x1fc62513,0xa7c3a62f,0x1cb2a0a5,0x27ea27a8,0xa4c49e3e,0xa66da7d9,0x26dd2472,0x241d26a7,0xa7fea70e,0x9648a38b,0x278827f6,0xa1641a46,
0x266d2800,0xa4c40000,0x26dd221f,0x241d2764,0xa16420a5,0xa788a7a8,0x25ed27f6,0xa55f9a46,0xa7fea6a7,0x1648a472,0xa2d71e3e,0xa73ba7d9,
0x9fc6a62f,0x27c32513,0xa7eaa70e,0x1cb2a38b,0x255f2800,0xa5ed0000,0x21642764,0xa788a21f,0xa66d9a46,0xa4c4a7f6,0xa7c3a38b,0x9fc6a70e,
0xa41da7d9,0x26dd1e3e,0x9cb2a6a7,0x27ea2472,0x273b20a5,0x22d727a8,0x27fe2513,0x1648262f,0x241d2800,0xa6dd0000,0xa7eaa21f,0x9cb2a764,
0xa7fea38b,0x9648a70e,0x2164a513,0x2788262f,0x22d7a472,0x273b26a7,0x255f27d9,0xa5ed1e3e,0x24c427f6,0xa66d1a46,0xa7c3a0a5,0x9fc6a7a8,
0x21642800,0xa7880000,0x1648a764,0x27fe221f,0xa6dda62f,0x241da513,0x24c427a8,0xa66d20a5,0x27ea1e3e,0x1cb227d9,0xa7c3a472,0x1fc6a6a7,
0xa55f238b,0xa5eda70e,0x273b9a46,0x22d727f6,0x1cb22800,0xa7ea0000,0x27c3221f,0x9fc62764,0xa2d7a7a8,0x273ba0a5,0xa7fe9a46,0x9648a7f6,
0x255f26a7,0xa5ed2472,0x27889e3e,0x216427d9,0xa6dda513,0x241da62f,0xa66d238b,0xa4c4a70e,0x96482800,0xa7fe0000,0xa2d72764,0xa73ba21f,
0x1cb2a7f6,0x27ea1a46,0x241da70e,0x26dd238b,0x9fc627d9,0xa7c39e3e,0xa4c426a7,0xa66da472,0x2164a7a8,0x278820a5,0x255fa62f,0x25ed2513,
0x9fc62800,0xa7c30000,0xa66da21f,0x24c4a764,0x255fa70e,0x25ed238b,0x22d7262f,0xa73b2513,0xa7882472,0xa164a6a7,0x1648a7d9,0x27fe9e3e,
0x27ea9a46,0x9cb227f6,0xa41d27a8,0xa6dda0a5,0xa2d72800,0xa73b0000,0x25eda764,0x255f221f,0x27c3a513,0x1fc6262f,0xa7ea20a5,0x1cb2a7a8,
0xa66d9e3e,0x24c4a7d9,0x241d2472,0xa6dd26a7,0x1648270e,0xa7fe238b,0x2164a7f6,0x27889a46,0xa4c42800,0xa66d0000,0x241d221f,0xa6dd2764,
0x2788a0a5,0xa16427a8,0x255fa7f6,0x25ed1a46,0x1648a6a7,0x27fea472,0xa73b1e3e,0x22d7a7d9,0xa7c3262f,0x9fc6a513,0x9cb2270e,0xa7ea238b,
0xa5ed2800,0xa55f0000,0xa7882764,0xa164a21f,0x24c41a46,0xa66d27f6,0x1fc6238b,0xa7c3270e,0x26dda7d9,0x241d1e3e,0x27eaa6a7,0x1cb22472,
0xa2d7a0a5,0x273ba7a8,0x9648a513,0x27fea62f,0xa6dd2800,0xa41d0000,0x9cb2a21f,0x27eaa764,0x1648238b,0xa7fe270e,0xa7882513,0x2164a62f,
0x273ba472,0xa2d726a7,0xa5ed27d9,0xa55f1e3e,0x266da7f6,0x24c49a46,0x1fc620a5,0xa7c327a8,0xa7882800,0xa1640000,0x27fea764,0x9648221f,
0xa41d262f,0xa6dd2513,0x266da7a8,0x24c4a0a5,0x1cb21e3e,0xa7ea27d9,0x1fc6a472,0x27c3a6a7,0x25eda38b,0xa55f270e,0xa2d71a46,0x273ba7f6,
0xa7ea2800,0x9cb20000,0x9fc6221f,0xa7c32764,0xa73b27a8,0xa2d720a5,0x16481a46,0xa7fe27f6,0xa5ed26a7,0xa55f2472,0x21649e3e,0xa78827d9,
0xa41d2513,0xa6dd262f,0x24c4a38b,0xa66d270e,0xa7fe2800,0x16480000,0xa73b2764,0x22d7a21f,0xa7ea27f6,0x1cb29a46,0xa6dd270e,0x241da38b,
0xa7c327d9,0x1fc69e3e,0xa66d26a7,0x24c4a472,0xa78827a8,0x2164a0a5,0xa5ed262f,0x255fa513,0xa7c32800,0x1fc60000,0x24c4a21f,0x266da764,
0xa5ed270e,0x255fa38b,0x273ba62f,0x22d7a513,0xa1642472,0x2788a6a7,0x27fea7d9,0x96489e3e,0x1cb21a46,0x27eaa7f6,0x26dda7a8,0xa41d20a5,
0xa73b2800,0x22d70000,0x255fa764,0xa5ed221f,0x9fc62513,0x27c3a62f,0x9cb2a0a5,0xa7ea27a8,0x24c49e3e,0x266da7d9,0xa6dd2472,0xa41d26a7,
0x27fea70e,0x1648a38b,0xa78827f6,0x21641a46,0xa66d2800,0x24c40000,0xa6dd221f,0xa41d2764,0x216420a5,0x2788a7a8,0xa5ed27f6,0x255f9a46,
0x27fea6a7,0x9648a472,0x22d71e3e,0x273ba7d9,0x1fc6a62f,0xa7c32513,0x27eaa70e,0x9cb2a38b,0xa55f2800,0x25ed0000,0xa1642764,0x2788a21f,
0x266d9a46,0x24c4a7f6,0x27c3a38b,0x1fc6a70e,0x241da7d9,0xa6dd1e3e,0x1cb2a6a7,0xa7ea2472,0xa73b20a5,0xa2d727a8,0xa7fe2513,0x9648262f,
0xa41d2800,0x26dd0000,0x27eaa21f,0x1cb2a764,0x27fea38b,0x1648a70e,0xa164a513,0xa788262f,0xa2d7a472,0xa73b26a7,0xa55f27d9,0x25ed1e3e,
0xa4c427f6,0x266d1a46,0x27c3a0a5,0x1fc6a7a8,0xa1642800,0x27880000,0x9648a764,0xa7fe221f,0x26dda62f,0xa41da513,0xa4c427a8,0x266d20a5,
0xa7ea1e3e,0x9cb227d9,0x27c3a472,0x9fc6a6a7,0x255f238b,0x25eda70e,0xa73b9a46,0xa2d727f6,0x9cb22800,0x27ea0000,0xa7c3221f,0x1fc62764,
0x22d7a7a8,0xa73ba0a5,0x27fe9a46,0x1648a7f6,0xa55f26a7,0x25ed2472,0xa7889e3e,0xa16427d9,0x26dda513,0xa41da62f,0x266d238b,0x24c4a70e,
0x16482800,0x27fe0000,0x22d72764,0x273ba21f,0x9cb2a7f6,0xa7ea1a46,0xa41da70e,0xa6dd238b,0x1fc627d9,0x27c39e3e,0x24c426a7,0x266da472,
0xa164a7a8,0xa78820a5,0xa55fa62f,0xa5ed2513,0x1fc62800,0x27c30000,0x266da21f,0xa4c4a764,0xa55fa70e,0xa5ed238b,0xa2d7262f,0x273b2513,
0x27882472,0x2164a6a7,0x9648a7d9,0xa7fe9e3e,0xa7ea9a46,0x1cb227f6,0x241d27a8,0x26dda0a5,0x22d72800,0x273b0000,0xa5eda764,0xa55f221f,
0xa7c3a513,0x9fc6262f,0x27ea20a5,0x9cb2a7a8,0x266d9e3e,0xa4c4a7d9,0xa41d2472,0x26dd26a7,0x9648270e,0x27fe238b,0xa164a7f6,0xa7889a46,
0x24c42800,0x266d0000,0xa41d221f,0x26dd2764,0xa788a0a5,0x216427a8,0xa55fa7f6,0xa5ed1a46,0x9648a6a7,0xa7fea472,0x273b1e3e,0xa2d7a7d9,
0x27c3262f,0x1fc6a513,0x1cb2270e,0x27ea238b,0x25ed2800,0x255f0000,0x27882764,0x2164a21f,0xa4c41a46,0x266d27f6,0x9fc6238b,0x27c3270e,
0xa6dda7d9,0xa41d1e3e,0xa7eaa6a7,0x9cb22472,0x22d7a0a5,0xa73ba7a8,0x1648a513,0xa7fea62f,0x26dd2800,0x241d0000,0x1cb2a21f,0xa7eaa764,
0x9648238b,0x27fe270e,0x27882513,0xa164a62f,0xa73ba472,0x22d726a7,0x25ed27d9,0x255f1e3e,0xa66da7f6,0xa4c49a46,0x9fc620a5,0x27c327a8,
0x27882800,0x21640000,0xa7fea764,0x1648221f,0x241d262f,0x26dd2513,0xa66da7a8,0xa4c4a0a5,0x9cb21e3e,0x27ea27d9,0x9fc6a472,0xa7c3a6a7,
0xa5eda38b,0x255f270e,0x22d71a46,0xa73ba7f6,0x27ea2800,0x1cb20000,0x1fc6221f,0x27c32764,0x273b27a8,0x22d720a5,0x96481a46,0x27fe27f6,
0x25ed26a7,0x255f2472,0xa1649e3e,0x278827d9,0x241d2513,0x26dd262f,0xa4c4a38b,0x266d270e,0x255f25a8,0xa5eda5a8,0x2164221f,0xa788a764,
0x24c42513,0xa66da62f,0x1fc620a5,0xa7c3a7a8,0x241d2472,0xa6dda6a7,0x1cb21e3e,0xa7eaa7d9,0x22d7238b,0xa73ba70e,0x16481a46,0xa7fea7f6,
0xa41da5a8,0x26dd25a8,0x27ea2764,0x1cb2221f,0x9648a0a5,0x27fe27a8,0x278827f6,0xa1649a46,0x22d71e3e,0x273b27d9,0x255f26a7,0xa5eda472,
0x266d2513,0x24c4262f,0x1fc6238b,0xa7c3a70e,0x216425a8,0xa788a5a8,0x1648a21f,0x27fe2764,0xa41d9a46,0xa6dda7f6,0x266d238b,0x24c4270e,
0xa7eaa6a7,0x9cb2a472,0x27c327d9,0x9fc61e3e,0xa5eda7a8,0x255f20a5,0x22d7262f,0xa73ba513,0x9cb2a5a8,0x27ea25a8,0xa7c3a764,0x1fc6a21f,
0x273b238b,0x22d7270e,0x9648a513,0x27fe262f,0x255f27d9,0xa5ed9e3e,0x27882472,0x216426a7,0xa41d1a46,0xa6dda7f6,0x24c427a8,0xa66da0a5,
0x964825a8,0xa7fea5a8,0xa2d7221f,0xa73ba764,0xa7eaa62f,0x1cb2a513,0xa6dda7a8,0x241da0a5,0x1fc6a472,0x27c326a7,0x24c49e3e,0x266d27d9,
0x2788270e,0xa164238b,0x25ed27f6,0xa55f1a46,0x1fc6a5a8,0x27c325a8,0x266d2764,0xa4c4221f,0x25ed27a8,0xa55f20a5,0xa73b9a46,0xa2d7a7f6,
0xa7889e3e,0xa164a7d9,0x1648a6a7,0x27fe2472,0x1cb2a62f,0x27ea2513,0x26dd270e,0xa41d238b,0xa2d725a8,0xa73ba5a8,0x25eda21f,0x255f2764,
0x9fc6a7f6,0x27c31a46,0x9cb2270e,0xa7eaa38b,0x266d26a7,0xa4c42472,0xa41da7d9,0x26dd9e3e,0xa7fea0a5,0x9648a7a8,0x27882513,0xa164262f,
0x24c4a5a8,0x266d25a8,0xa41da764,0x26dda21f,0xa164270e,0xa788a38b,0x25ed262f,0xa55f2513,0x1648a7d9,0x27fe1e3e,0xa73ba472,0x22d7a6a7,
0x1fc627f6,0xa7c31a46,0x27ea20a5,0x9cb227a8,0xa5ed25a8,0xa55fa5a8,0xa788221f,0xa164a764,0x266da513,0x24c4262f,0x27c3a0a5,0x1fc627a8,
0xa6dd2472,0xa41da6a7,0xa7ea1e3e,0x9cb2a7d9,0x273ba38b,0x22d7270e,0x27fe9a46,0x164827f6,0x26dda5a8,0x241d25a8,0x1cb22764,0xa7ea221f,
0xa7fe20a5,0x9648a7a8,0x2164a7f6,0x27881a46,0x273b1e3e,0xa2d727d9,0xa5ed26a7,0xa55fa472,0xa4c4a513,0x266da62f,0x27c3a38b,0x1fc6270e,
0xa78825a8,0xa164a5a8,0x27fea21f,0x96482764,0x26dd1a46,0xa41d27f6,0xa4c4a38b,0x266da70e,0x9cb2a6a7,0x27eaa472,0x9fc627d9,0xa7c31e3e,
0xa55f27a8,0xa5eda0a5,0x273ba62f,0x22d72513,0x27eaa5a8,0x1cb225a8,0x1fc6a764,0x27c3a21f,0xa2d7a38b,0x273ba70e,0xa7fe2513,0x9648a62f,
0xa5ed27d9,0xa55f9e3e,0x21642472,0xa78826a7,0x26dd9a46,0xa41d27f6,0x266da7a8,0x24c420a5,0xa7fe25a8,0x1648a5a8,0xa73b221f,0x22d7a764,
0x9cb2262f,0xa7ea2513,0xa41d27a8,0xa6dd20a5,0x27c3a472,0x9fc626a7,0x266d9e3e,0xa4c427d9,0x2164a70e,0x2788a38b,0x255fa7f6,0x25ed9a46,
0x27c3a5a8,0x9fc625a8,0xa4c42764,0xa66d221f,0x255fa7a8,0x25eda0a5,0x22d71a46,0xa73b27f6,0xa1649e3e,0x2788a7d9,0x27fea6a7,0x96482472,
0xa7ea262f,0x1cb2a513,0x241da70e,0x26dda38b,0xa73b25a8,0x22d7a5a8,0x255fa21f,0xa5ed2764,0xa7c327f6,0x9fc69a46,0x27eaa70e,0x9cb2238b,
0xa4c426a7,0xa66d2472,0x26dda7d9,0x241d9e3e,0x164820a5,0xa7fe27a8,0x2164a513,0x2788a62f,0x266da5a8,0xa4c425a8,0x26dda764,0x241da21f,
0x2788a70e,0xa164238b,0x255fa62f,0x25eda513,0x27fea7d9,0x96481e3e,0x22d7a472,0x273ba6a7,0x27c3a7f6,0x1fc69a46,0x1cb2a0a5,0x27eaa7a8,
0xa55f25a8,0x25eda5a8,0xa164221f,0x2788a764,0xa4c42513,0x266da62f,0x9fc620a5,0x27c3a7a8,0xa41d2472,0x26dda6a7,0x9cb21e3e,0x27eaa7d9,
0xa2d7238b,0x273ba70e,0x96481a46,0x27fea7f6,0x241da5a8,0xa6dd25a8,0xa7ea2764,0x9cb2221f,0x1648a0a5,0xa7fe27a8,0xa78827f6,0x21649a46,
0xa2d71e3e,0xa73b27d9,0xa55f26a7,0x25eda472,0xa66d2513,0xa4c4262f,0x9fc6238b,0x27c3a70e,0xa16425a8,0x2788a5a8,0x9648a21f,0xa7fe2764,
0x241d9a46,0x26dda7f6,0xa66d238b,0xa4c4270e,0x27eaa6a7,0x1cb2a472,0xa7c327d9,0x1fc61e3e,0x25eda7a8,0xa55f20a5,0xa2d7262f,0x273ba513,
0x1cb2a5a8,0xa7ea25a8,0x27c3a764,0x9fc6a21f,0xa73b238b,0xa2d7270e,0x1648a513,0xa7fe262f,0xa55f27d9,0x25ed9e3e,0xa7882472,0xa16426a7,
0x241d1a46,0x26dda7f6,0xa4c427a8,0x266da0a5,0x164825a8,0x27fea5a8,0x22d7221f,0x273ba764,0x27eaa62f,0x9cb2a513,0x26dda7a8,0xa41da0a5,
0x9fc6a472,0xa7c326a7,0xa4c49e3e,0xa66d27d9,0xa788270e,0x2164238b,0xa5ed27f6,0x255f1a46,0x9fc6a5a8,0xa7c325a8,0xa66d2764,0x24c4221f,
0xa5ed27a8,0x255f20a5,0x273b9a46,0x22d7a7f6,0x27889e3e,0x2164a7d9,0x9648a6a7,0xa7fe2472,0x9cb2a62f,0xa7ea2513,0xa6dd270e,0x241d238b,
0x22d725a8,0x273ba5a8,0xa5eda21f,0xa55f2764,0x1fc6a7f6,0xa7c31a46,0x1cb2270e,0x27eaa38b,0xa66d26a7,0x24c42472,0x241da7d9,0xa6dd9e3e,
0x27fea0a5,0x1648a7a8,0xa7882513,0x2164262f,0xa4c4a5a8,0xa66d25a8,0x241da764,0xa6dda21f,0x2164270e,0x2788a38b,0xa5ed262f,0x255f2513,
0x9648a7d9,0xa7fe1e3e,0x273ba472,0xa2d7a6a7,0x9fc627f6,0x27c31a46,0xa7ea20a5,0x1cb227a8,0x25ed25a8,0x255fa5a8,0x2788221f,0x2164a764,
0xa66da513,0xa4c4262f,0xa7c3a0a5,0x9fc627a8,0x26dd2472,0x241da6a7,0x27ea1e3e,0x1cb2a7d9,0xa73ba38b,0xa2d7270e,0xa7fe9a46,0x964827f6,
0xa6dda5a8,0xa41d25a8,0x9cb22764,0x27ea221f,0x27fe20a5,0x1648a7a8,0xa164a7f6,0xa7881a46,0xa73b1e3e,0x22d727d9,0x25ed26a7,0x255fa472,
0x24c4a513,0xa66da62f,0xa7c3a38b,0x9fc6270e,0x278825a8,0x2164a5a8,0xa7fea21f,0x16482764,0xa6dd1a46,0x241d27f6,0x24c4a38b,0xa66da70e,
0x1cb2a6a7,0xa7eaa472,0x1fc627d9,0x27c31e3e,0x255f27a8,0x25eda0a5,0xa73ba62f,0xa2d72513,0xa7eaa5a8,0x9cb225a8,0x9fc6a764,0xa7c3a21f,
0x22d7a38b,0xa73ba70e,0x27fe2513,0x1648a62f,0x25ed27d9,0x255f9e3e,0xa1642472,0x278826a7,0xa6dd9a46,0x241d27f6,0xa66da7a8,0xa4c420a5,
0x27fe25a8,0x9648a5a8,0x273b221f,0xa2d7a764,0x1cb2262f,0x27ea2513,0x241d27a8,0x26dd20a5,0xa7c3a472,0x1fc626a7,0xa66d9e3e,0x24c427d9,
0xa164a70e,0xa788a38b,0xa55fa7f6,0xa5ed9a46,0xa7c3a5a8,0x1fc625a8,0x24c42764,0x266d221f,0xa55fa7a8,0xa5eda0a5,0xa2d71a46,0x273b27f6,
0x21649e3e,0xa788a7d9,0xa7fea6a7,0x16482472,0x27ea262f,0x9cb2a513,0xa41da70e,0xa6dda38b,0x273b25a8,0xa2d7a5a8,0xa55fa21f,0x25ed2764,
0x27c327f6,0x1fc69a46,0xa7eaa70e,0x1cb2238b,0x24c426a7,0x266d2472,0xa6dda7d9,0xa41d9e3e,0x964820a5,0x27fe27a8,0xa164a513,0xa788a62f,
0xa66da5a8,0x24c425a8,0xa6dda764,0xa41da21f,0xa788a70e,0x2164238b,0xa55fa62f,0xa5eda513,0xa7fea7d9,0x16481e3e,0xa2d7a472,0xa73ba6a7,
0xa7c3a7f6,0x9fc69a46,0x9cb2a0a5,0xa7eaa7a8,
};

#define PROF(slot) do {} while (0)
#define PROF3(slot) do {} while (0)
#define PROF2(slot) do {} while (0)

__device__ __forceinline__ uint32_t smem_u32(const void* p) { return (uint32_t)__cvta_generic_to_shared(p); }

__device__ __forceinline__ void mbar_init(uint32_t a, uint32_t c) {
  asm volatile("mbarrier.init.shared::cta.b64 [%0], %1;\n" ::"r"(a), "r"(c) : "memory");
}
__device__ __forceinline__ void mbar_expect_tx(uint32_t a, uint32_t bytes) {
  asm volatile("mbarrier.arrive.expect_tx.shared::cta.b64 _, [%0], %1;\n" ::"r"(a), "r"(bytes) : "memory");
}
__device__ __forceinline__ void mbar_arrive_cluster(uint32_t cluster_addr) {
  asm volatile("mbarrier.arrive.shared::cluster.b64 _, [%0];\n" ::"r"(cluster_addr) : "memory");
}
__device__ __forceinline__ void mbar_arrive_cluster_n(uint32_t cluster_addr, uint32_t n) {
  asm volatile("mbarrier.arrive.shared::cluster.b64 _, [%0], %1;\n" ::"r"(cluster_addr), "r"(n) : "memory");
}
__device__ __forceinline__ bool mbar_try(uint32_t a, uint32_t parity) {
  uint32_t ok;
  asm volatile("{\n.reg .pred p;\nmbarrier.try_wait.parity.shared::cta.b64 p, [%1], %2;\nselp.u32 %0, 1, 0, p;\n}\n"
               : "=r"(ok) : "r"(a), "r"(parity) : "memory");
  return ok;
}
__device__ __forceinline__ void mbar_wait(uint32_t a, uint32_t parity) {
  if (mbar_try(a, parity)) return;
#pragma unroll 1
  for (int n = 0; n < SPIN_LIMIT; n++)
    if (mbar_try(a, parity)) break;
}
__device__ __forceinline__ bool elect_one() {
  uint32_t p;
  asm volatile("{\n.reg .pred P;\nelect.sync _|P, 0xffffffff;\nselp.u32 %0, 1, 0, P;\n}\n" : "=r"(p));
  return p;
}
__device__ __forceinline__ uint32_t mapa(uint32_t a, uint32_t rank) {
  uint32_t r;
  asm volatile("mapa.shared::cluster.u32 %0, %1, %2;\n" : "=r"(r) : "r"(a), "r"(rank));
  return r;
}
__device__ __forceinline__ void nb_sync(int id, int n) { asm volatile("bar.sync %0, %1;\n" ::"r"(id), "r"(n) : "memory"); }
__device__ __forceinline__ void nb_arrive(int id, int n) { asm volatile("bar.arrive %0, %1;\n" ::"r"(id), "r"(n) : "memory"); }
__device__ __forceinline__ void cluster_sync_all() {
  asm volatile("barrier.cluster.arrive.relaxed.aligned;\nbarrier.cluster.wait.aligned;\n" ::: "memory");
}
__device__ __forceinline__ void fence_async_smem() { asm volatile("fence.proxy.async.shared::cta;\n" ::: "memory"); }
__device__ __forceinline__ void fence_async_all() { asm volatile("fence.proxy.async.global;\n" ::: "memory"); }

__device__ __forceinline__ void tma_load_3d(uint32_t dst, const CUtensorMap* tm, uint32_t bar, int c0, int c1, int c2) {
  asm volatile(
      "cp.async.bulk.tensor.3d.shared::cluster.global.mbarrier::complete_tx::bytes [%0], [%1, {%3, %4, %5}], [%2];\n"
      ::"r"(dst), "l"(tm), "r"(bar), "r"(c0), "r"(c1), "r"(c2) : "memory");
}
__device__ __forceinline__ void tma_load_4d(uint32_t dst, const CUtensorMap* tm, uint32_t bar, int c0, int c1, int c2, int c3) {
  asm volatile(
      "cp.async.bulk.tensor.4d.shared::cluster.global.mbarrier::complete_tx::bytes [%0], [%1, {%3, %4, %5, %6}], [%2];\n"
      ::"r"(dst), "l"(tm), "r"(bar), "r"(c0), "r"(c1), "r"(c2), "r"(c3) : "memory");
}
__device__ __forceinline__ void tma_load_3d_mc(uint32_t dst, const CUtensorMap* tm, uint32_t bar, int c0, int c1, int c2) {
  asm volatile(
      "cp.async.bulk.tensor.3d.shared::cluster.global.mbarrier::complete_tx::bytes.multicast::cluster [%0], [%1, {%3, %4, %5}], [%2], %6;\n"
      ::"r"(dst), "l"(tm), "r"(bar), "r"(c0), "r"(c1), "r"(c2), "h"((uint16_t)3) : "memory");
}
__device__ __forceinline__ void tma_load_2d(uint32_t dst, const CUtensorMap* tm, uint32_t bar, int c0, int c1) {
  asm volatile(
      "cp.async.bulk.tensor.2d.shared::cluster.global.mbarrier::complete_tx::bytes [%0], [%1, {%3, %4}], [%2];\n"
      ::"r"(dst), "l"(tm), "r"(bar), "r"(c0), "r"(c1) : "memory");
}
__device__ __forceinline__ void bulk_load(uint32_t dst, const void* src, uint32_t bytes, uint32_t bar) {
  asm volatile("cp.async.bulk.shared::cluster.global.mbarrier::complete_tx::bytes [%0], [%1], %2, [%3];\n"
               ::"r"(dst), "l"(src), "r"(bytes), "r"(bar) : "memory");
}
__device__ __forceinline__ void bulk_commit() { asm volatile("cp.async.bulk.commit_group;\n" ::: "memory"); }
__device__ __forceinline__ void bulk_wait0() { asm volatile("cp.async.bulk.wait_group 0;\n" ::: "memory"); }
__device__ __forceinline__ void prefetch_tmap(const CUtensorMap* tm) {
  asm volatile("prefetch.tensormap [%0];\n" ::"l"(tm) : "memory");
}

__device__ __forceinline__ void wg_fence() { asm volatile("wgmma.fence.sync.aligned;\n" ::: "memory"); }
__device__ __forceinline__ void wg_commit() { asm volatile("wgmma.commit_group.sync.aligned;\n" ::: "memory"); }
template <int N> __device__ __forceinline__ void wg_wait() {
  asm volatile("wgmma.wait_group.sync.aligned %0;\n" ::"n"(N) : "memory");
}
__device__ __forceinline__ uint64_t mkdesc(uint32_t addr, uint32_t lbo, uint32_t sbo, uint32_t swz) {
  return (uint64_t)((addr & 0x3FFFF) >> 4) | ((uint64_t)(lbo >> 4) << 16) | ((uint64_t)(sbo >> 4) << 32) |
         ((uint64_t)swz << 62);
}

#define R4(d, o) "+f"(d[o + 0]), "+f"(d[o + 1]), "+f"(d[o + 2]), "+f"(d[o + 3])
#define R8(d, o) R4(d, o), R4(d, o + 4)
#define R16(d, o) R8(d, o), R8(d, o + 8)
#define R32(d, o) R16(d, o), R16(d, o + 16)
#define R64(d, o) R32(d, o), R32(d, o + 32)

__device__ __forceinline__ void wgmma_n192(float (&d)[96], uint64_t da, uint64_t db, uint32_t acc) {
  asm volatile(
      "{\n.reg .pred p;\nsetp.ne.u32 p, %98, 0;\n"
      "wgmma.mma_async.sync.aligned.m64n192k16.f32.bf16.bf16 "
      "{%0,%1,%2,%3,%4,%5,%6,%7,%8,%9,%10,%11,%12,%13,%14,%15,%16,%17,%18,%19,%20,%21,%22,%23,%24,%25,%26,%27,%28,%29,%30,%31,"
      "%32,%33,%34,%35,%36,%37,%38,%39,%40,%41,%42,%43,%44,%45,%46,%47,%48,%49,%50,%51,%52,%53,%54,%55,%56,%57,%58,%59,%60,%61,%62,%63,"
      "%64,%65,%66,%67,%68,%69,%70,%71,%72,%73,%74,%75,%76,%77,%78,%79,%80,%81,%82,%83,%84,%85,%86,%87,%88,%89,%90,%91,%92,%93,%94,%95}, "
      "%96, %97, p, 1, 1, 0, 1;\n}\n"
      : R64(d, 0), R32(d, 64)
      : "l"(da), "l"(db), "r"(acc));
}
__device__ __forceinline__ void wgmma_n128(float (&d)[64], uint64_t da, uint64_t db, uint32_t acc) {
  asm volatile(
      "{\n.reg .pred p;\nsetp.ne.u32 p, %66, 0;\n"
      "wgmma.mma_async.sync.aligned.m64n128k16.f32.bf16.bf16 "
      "{%0,%1,%2,%3,%4,%5,%6,%7,%8,%9,%10,%11,%12,%13,%14,%15,%16,%17,%18,%19,%20,%21,%22,%23,%24,%25,%26,%27,%28,%29,%30,%31,"
      "%32,%33,%34,%35,%36,%37,%38,%39,%40,%41,%42,%43,%44,%45,%46,%47,%48,%49,%50,%51,%52,%53,%54,%55,%56,%57,%58,%59,%60,%61,%62,%63}, "
      "%64, %65, p, 1, 1, 0, 1;\n}\n"
      : R64(d, 0)
      : "l"(da), "l"(db), "r"(acc));
}
template <int N> __device__ __forceinline__ void fence_regs(float (&d)[N]) {
#pragma unroll
  for (int i = 0; i < N; i++) asm volatile("" : "+f"(d[i])::"memory");
}

__device__ __forceinline__ void mma16816(float (&d)[4], uint32_t a0, uint32_t a1, uint32_t a2, uint32_t a3, uint32_t b0,
                                         uint32_t b1) {
  asm("mma.sync.aligned.m16n8k16.row.col.f32.bf16.bf16.f32 {%0,%1,%2,%3}, {%4,%5,%6,%7}, {%8,%9}, {%0,%1,%2,%3};\n"
      : "+f"(d[0]), "+f"(d[1]), "+f"(d[2]), "+f"(d[3])
      : "r"(a0), "r"(a1), "r"(a2), "r"(a3), "r"(b0), "r"(b1));
}
__device__ __forceinline__ void mma16816_z(float (&d)[4], uint32_t a0, uint32_t a1, uint32_t a2, uint32_t a3, uint32_t b0,
                                           uint32_t b1) {
  asm("mma.sync.aligned.m16n8k16.row.col.f32.bf16.bf16.f32 {%0,%1,%2,%3}, {%4,%5,%6,%7}, {%8,%9}, {%10,%10,%10,%10};\n"
      : "=f"(d[0]), "=f"(d[1]), "=f"(d[2]), "=f"(d[3])
      : "r"(a0), "r"(a1), "r"(a2), "r"(a3), "r"(b0), "r"(b1), "f"(0.f));
}
__device__ __forceinline__ void ldsm4t(uint32_t (&r)[4], uint32_t a) {
  asm volatile("ldmatrix.sync.aligned.m8n8.x4.trans.shared.b16 {%0,%1,%2,%3}, [%4];\n"
               : "=r"(r[0]), "=r"(r[1]), "=r"(r[2]), "=r"(r[3]) : "r"(a) : "memory");
}
__device__ __forceinline__ void ldsm2t(uint32_t& r0, uint32_t& r1, uint32_t a) {
  asm volatile("ldmatrix.sync.aligned.m8n8.x2.trans.shared.b16 {%0,%1}, [%2];\n" : "=r"(r0), "=r"(r1) : "r"(a) : "memory");
}
__device__ __forceinline__ void st_async128(uint32_t a, uint32_t bar, uint32_t x, uint32_t y, uint32_t z, uint32_t w) {
  asm volatile("st.async.weak.shared::cluster.mbarrier::complete_tx::bytes.v4.b32 [%0], {%2,%3,%4,%5}, [%1];\n"
               ::"r"(a), "r"(bar), "r"(x), "r"(y), "r"(z), "r"(w) : "memory");
}
__device__ __forceinline__ void mbar_arrive(uint32_t a) {
  asm volatile("mbarrier.arrive.shared::cta.b64 _, [%0];\n" ::"r"(a) : "memory");
}
__device__ __forceinline__ void stsm4(uint32_t a, uint32_t r0, uint32_t r1, uint32_t r2, uint32_t r3) {
  asm volatile("stmatrix.sync.aligned.m8n8.x4.shared.b16 [%0], {%1,%2,%3,%4};\n"
               ::"r"(a), "r"(r0), "r"(r1), "r"(r2), "r"(r3) : "memory");
}
__device__ __forceinline__ void stsm4t(uint32_t a, uint32_t r0, uint32_t r1, uint32_t r2, uint32_t r3) {
  asm volatile("stmatrix.sync.aligned.m8n8.x4.trans.shared.b16 [%0], {%1,%2,%3,%4};\n"
               ::"r"(a), "r"(r0), "r"(r1), "r"(r2), "r"(r3) : "memory");
}
__device__ __forceinline__ uint2 lds64(uint32_t a) {
  uint2 v;
  asm volatile("ld.shared.v2.u32 {%0,%1}, [%2];\n" : "=r"(v.x), "=r"(v.y) : "r"(a));
  return v;
}
__device__ __forceinline__ uint4 lds128(uint32_t a) {
  uint4 v;
  asm volatile("ld.shared.v4.u32 {%0,%1,%2,%3}, [%4];\n" : "=r"(v.x), "=r"(v.y), "=r"(v.z), "=r"(v.w) : "r"(a) : "memory");
  return v;
}
__device__ __forceinline__ void sts128(uint32_t a, uint32_t x, uint32_t y, uint32_t z, uint32_t w) {
  asm volatile("st.shared.v4.u32 [%0], {%1,%2,%3,%4};\n" ::"r"(a), "r"(x), "r"(y), "r"(z), "r"(w) : "memory");
}
__device__ __forceinline__ uint32_t pack_bf16(float lo, float hi) {
  uint32_t r;
  asm("cvt.rn.bf16x2.f32 %0, %1, %2;\n" : "=r"(r) : "f"(hi), "f"(lo));
  return r;
}
__device__ __forceinline__ uint32_t bmul2(uint32_t a, uint32_t b) {
  uint32_t r;
  asm("mul.rn.bf16x2 %0, %1, %2;\n" : "=r"(r) : "r"(a), "r"(b));
  return r;
}
__device__ __forceinline__ uint32_t bmax2(uint32_t a, uint32_t b) {
  uint32_t r;
  asm("max.bf16x2 %0, %1, %2;\n" : "=r"(r) : "r"(a), "r"(b));
  return r;
}
__device__ __forceinline__ uint32_t bfma2(uint32_t a, uint32_t b, uint32_t c) {
  uint32_t r;
  asm("fma.rn.bf16x2 %0, %1, %2, %3;\n" : "=r"(r) : "r"(a), "r"(b), "r"(c));
  return r;
}
__device__ __forceinline__ uint32_t badd2(uint32_t a, uint32_t b) {
  uint32_t r;
  asm("add.rn.bf16x2 %0, %1, %2;\n" : "=r"(r) : "r"(a), "r"(b));
  return r;
}
__device__ __forceinline__ void prefetch_l2(const void* p) { asm volatile("prefetch.global.L2 [%0];\n" ::"l"(p)); }
__device__ __forceinline__ void cp_async16n(uint32_t dst, const void* src) {
  asm volatile("cp.async.cg.shared.global [%0], [%1], 16;\n" ::"r"(dst), "l"(src) : "memory");
}
__device__ __forceinline__ void cp_async16(uint32_t dst, const void* src, uint32_t srcbytes) {
  asm volatile("cp.async.cg.shared.global.L2::256B [%0], [%1], 16, %2;\n" ::"r"(dst), "l"(src), "r"(srcbytes) : "memory");
}
__device__ __forceinline__ uint32_t ld_acquire(const uint32_t* p) {
  uint32_t v;
  asm volatile("ld.acquire.gpu.global.u32 %0, [%1];\n" : "=r"(v) : "l"(p) : "memory");
  return v;
}
__device__ __forceinline__ uint32_t ld_relaxed(const uint32_t* p) {
  uint32_t v;
  asm volatile("ld.relaxed.gpu.global.u32 %0, [%1];\n" : "=r"(v) : "l"(p) : "memory");
  return v;
}
__device__ __forceinline__ void st_release(uint32_t* p, uint32_t v) {
  asm volatile("st.release.gpu.global.u32 [%0], %1;\n" ::"l"(p), "r"(v) : "memory");
}
__device__ __forceinline__ void wait_flag(const uint32_t* p, uint32_t want) {
  int n = 0;
  while (ld_relaxed(p) != want && ++n < SPIN_LIMIT) __nanosleep(40);
  (void)ld_acquire(p);
}

struct Params {
  const __nv_bfloat16* x;
  const __nv_bfloat16* w;
  const __nv_bfloat16* q;
  const __nv_bfloat16* k;
  const __nv_bfloat16* v;
  const __nv_bfloat16* shift_k;
  const __nv_bfloat16* ssm_k;
  const __nv_bfloat16* ssm_D;
  const __nv_bfloat16* wo;
  __nv_bfloat16* out;
};

__device__ __forceinline__ uint32_t lds32(uint32_t a) {
  uint32_t v;
  asm volatile("ld.shared.u32 %0, [%1];\n" : "=r"(v) : "r"(a));
  return v;
}
#define W4(d, o) "=f"(d[o + 0]), "=f"(d[o + 1]), "=f"(d[o + 2]), "=f"(d[o + 3])
#define W8(d, o) W4(d, o), W4(d, o + 4)
#define W16(d, o) W8(d, o), W8(d, o + 8)
#define U4(c, d, o) c(d[o + 0]), c(d[o + 1]), c(d[o + 2]), c(d[o + 3])
#define U8(c, d, o) U4(c, d, o), U4(c, d, o + 4)
#define U16(c, d, o) U8(c, d, o), U8(c, d, o + 8)
#define U32(c, d, o) U16(c, d, o), U16(c, d, o + 16)
#define D32 "{%0,%1,%2,%3,%4,%5,%6,%7,%8,%9,%10,%11,%12,%13,%14,%15,%16,%17,%18,%19,%20,%21,%22,%23,%24,%25,%26,%27,%28,%29,%30,%31}"
#define D16 "{%0,%1,%2,%3,%4,%5,%6,%7,%8,%9,%10,%11,%12,%13,%14,%15}"
#define D8 "{%0,%1,%2,%3,%4,%5,%6,%7}"
template <int ACC> __device__ __forceinline__ void hmma_n128t(uint32_t (&d)[32], const uint32_t (&a)[4], uint64_t db) {
  if (ACC)
    asm volatile("wgmma.mma_async.sync.aligned.m64n128k16.f16.f16.f16 " D32 ", {%32,%33,%34,%35}, %36, 1, 1, 1, 1;\n"
                 : U32("+r", d, 0) : "r"(a[0]), "r"(a[1]), "r"(a[2]), "r"(a[3]), "l"(db));
  else
    asm volatile("wgmma.mma_async.sync.aligned.m64n128k16.f16.f16.f16 " D32 ", {%32,%33,%34,%35}, %36, 0, 1, 1, 1;\n"
                 : U32("=r", d, 0) : "r"(a[0]), "r"(a[1]), "r"(a[2]), "r"(a[3]), "l"(db));
}
template <int ACC, int TB> __device__ __forceinline__ void hmma_n32(uint32_t (&d)[8], const uint32_t (&a)[4], uint64_t db) {
  if (ACC)
    asm volatile("wgmma.mma_async.sync.aligned.m64n32k16.f16.f16.f16 " D8 ", {%8,%9,%10,%11}, %12, 1, 1, 1, %13;\n"
                 : U8("+r", d, 0) : "r"(a[0]), "r"(a[1]), "r"(a[2]), "r"(a[3]), "l"(db), "n"(TB));
  else
    asm volatile("wgmma.mma_async.sync.aligned.m64n32k16.f16.f16.f16 " D8 ", {%8,%9,%10,%11}, %12, 0, 1, 1, %13;\n"
                 : U8("=r", d, 0) : "r"(a[0]), "r"(a[1]), "r"(a[2]), "r"(a[3]), "l"(db), "n"(TB));
}
template <int ACC> __device__ __forceinline__ void fmma_n32t(float (&d)[16], const uint32_t (&a)[4], uint64_t db) {
  if (ACC)
    asm volatile("wgmma.mma_async.sync.aligned.m64n32k16.f32.f16.f16 " D16 ", {%16,%17,%18,%19}, %20, 1, 1, 1, 1;\n"
                 : R16(d, 0) : "r"(a[0]), "r"(a[1]), "r"(a[2]), "r"(a[3]), "l"(db));
  else
    asm volatile("wgmma.mma_async.sync.aligned.m64n32k16.f32.f16.f16 " D16 ", {%16,%17,%18,%19}, %20, 0, 1, 1, 1;\n"
                 : W16(d, 0) : "r"(a[0]), "r"(a[1]), "r"(a[2]), "r"(a[3]), "l"(db));
}
template <int N> __device__ __forceinline__ void fence_regs(uint32_t (&d)[N]) {
#pragma unroll
  for (int i = 0; i < N; i++) asm volatile("" : "+r"(d[i])::"memory");
}
__device__ __forceinline__ uint32_t hmul(uint32_t a, uint32_t b) { uint32_t r; asm("mul.rn.f16x2 %0, %1, %2;\n" : "=r"(r) : "r"(a), "r"(b)); return r; }
__device__ __forceinline__ uint32_t hadd(uint32_t a, uint32_t b) { uint32_t r; asm("add.rn.f16x2 %0, %1, %2;\n" : "=r"(r) : "r"(a), "r"(b)); return r; }
__device__ __forceinline__ uint32_t hsub(uint32_t a, uint32_t b) { uint32_t r; asm("sub.rn.f16x2 %0, %1, %2;\n" : "=r"(r) : "r"(a), "r"(b)); return r; }
__device__ __forceinline__ uint32_t hfma(uint32_t a, uint32_t b, uint32_t c) { uint32_t r; asm("fma.rn.f16x2 %0, %1, %2, %3;\n" : "=r"(r) : "r"(a), "r"(b), "r"(c)); return r; }
__device__ __forceinline__ uint32_t hfnma(uint32_t a, uint32_t b, uint32_t c) {
  uint32_t r;
  asm("{\n.reg .b32 t;\nneg.f16x2 t, %1;\nfma.rn.f16x2 %0, t, %2, %3;\n}\n" : "=r"(r) : "r"(a), "r"(b), "r"(c));
  return r;
}
__device__ __forceinline__ uint32_t hrefl(uint32_t p, uint32_t s) {
  uint32_t r;
  asm("{\n.reg .b32 t;\nneg.f16x2 t, %2;\nfma.rn.f16x2 %0, %1, %3, t;\n}\n" : "=r"(r) : "r"(p), "r"(s), "r"(0x40004000u));
  return r;
}
__device__ __forceinline__ void bfly(uint32_t xr, uint32_t xi, uint32_t tr, uint32_t ti, uint32_t yr, uint32_t yi, uint32_t ur,
                                     uint32_t ui, uint32_t& sr, uint32_t& si, uint32_t& dr, uint32_t& di) {
  const uint32_t pr = hfnma(xi, ti, hmul(xr, tr)), pi = hfma(xi, tr, hmul(xr, ti));
  sr = hfnma(yi, ui, hfma(yr, ur, pr));
  si = hfma(yi, ur, hfma(yr, ui, pi));
  dr = hrefl(pr, sr);
  di = hrefl(pi, si);
}
template <int BH> __device__ __forceinline__ void fft_e1(const uint32_t (&d)[32], const uint32_t (&tw)[16], uint32_t (&a2)[2][2][4]) {
#pragma unroll
  for (int be = 0; be < 2; be++)
#pragma unroll
    for (int s = 0; s < 2; s++) {
      const int o = 16 * s + 8 * be + 2 * BH, p = 2 * BH;
      bfly(d[o], d[o + 1], tw[p], tw[p + 1], d[o + 4], d[o + 5], tw[p + 4], tw[p + 5], a2[be][0][s], a2[be][0][2 + s],
           a2[be][1][s], a2[be][1][2 + s]);
    }
}
__device__ __forceinline__ uint32_t hfms(uint32_t a, uint32_t b, uint32_t c) {
  uint32_t r;
  asm("{\n.reg .b32 t;\nneg.f16x2 t, %3;\nfma.rn.f16x2 %0, %1, %2, t;\n}\n" : "=r"(r) : "r"(a), "r"(b), "r"(c));
  return r;
}
template <int C, int J> __device__ __forceinline__ void fft_e2(const uint32_t (&d0)[8], const uint32_t (&d1)[8], uint32_t (&a3)[2][4]) {
  const uint32_t ur = d0[2 * J], ui = d0[4 + 2 * J], hr = d0[2 * J + 1], hi = d0[5 + 2 * J];
  const uint32_t vr = d1[2 * J], vi = d1[4 + 2 * J], gr = d1[2 * J + 1], gi = d1[5 + 2 * J];
  const uint32_t pr = hfnma(ui, hi, hmul(ur, hr)), pi = hfma(ui, hr, hmul(ur, hi));
  a3[0][C] = pr;
  a3[0][2 + C] = pi;
  a3[1][C] = hfnma(vi, hi, hfma(vr, hr, hfnma(ui, gi, hfms(ur, gr, pi))));
  a3[1][2 + C] = hfma(vi, hr, hfma(vr, hi, hfma(ui, gr, hfma(ur, gi, pr))));
}
__device__ __forceinline__ void fft_e3(const uint32_t (&d)[2][8], const uint32_t (&tw)[16], uint32_t zaddr) {
#pragma unroll
  for (int rho = 0; rho < 2; rho++) {
    uint32_t zr[4], zi[4];
#pragma unroll
    for (int nb = 0; nb < 4; nb++) {
      const uint32_t xr = d[nb >> 1][2 * (nb & 1) + rho], xi = d[nb >> 1][4 + 2 * (nb & 1) + rho];
      const uint32_t tr = tw[8 + 4 * rho + 2 * (nb & 1)], ti = tw[9 + 4 * rho + 2 * (nb & 1)];
      zr[nb] = hfnma(xi, ti, hmul(xr, tr));
      zi[nb] = hfma(xi, tr, hmul(xr, ti));
    }
    stsm4(zaddr + rho * 1024, zr[0], zr[1], zr[2], zr[3]);
    stsm4(zaddr + rho * 1024 + 512, zi[0], zi[1], zi[2], zi[3]);
  }
}
__device__ __forceinline__ float bf_lo(uint32_t v) {
  uint32_t r;
  asm("prmt.b32 %0, %1, 0, 0x1044;\n" : "=r"(r) : "r"(v));
  return __uint_as_float(r);
}
__device__ __forceinline__ float bf_hi(uint32_t v) { return __uint_as_float(v & 0xffff0000u); }
__device__ __forceinline__ uint32_t to_fp16(uint32_t (&x)[32]) {
  uint32_t m[2] = {x[0], x[1]};
#pragma unroll
  for (int i = 2; i < 32; i++) asm("max.xorsign.abs.bf16x2 %0, %0, %1;\n" : "+r"(m[i & 1]) : "r"(x[i]));
  asm("max.xorsign.abs.bf16x2 %0, %0, %1;\n" : "+r"(m[0]) : "r"(m[1]));
  const uint32_t e = max(__reduce_max_sync(0xffffffffu, max((m[0] >> 7) & 255u, (m[0] >> 23) & 255u)), 5u);
  const uint32_t sc = (259u - e) * 0x00800080u;
#pragma unroll
  for (int i = 0; i < 32; i++) {
    const uint32_t v = bmul2(x[i], sc);
    asm("cvt.rn.f16x2.f32 %0, %1, %2;\n" : "=r"(x[i]) : "f"(bf_hi(v)), "f"(bf_lo(v)));
  }
  return e;
}
__device__ __forceinline__ float ex2(float x) {
  float r;
  asm("ex2.approx.ftz.f32 %0, %1;\n" : "=f"(r) : "f"(x));
  return r;
}
__device__ __forceinline__ float rcp(float x) {
  float r;
  asm("rcp.approx.ftz.f32 %0, %1;\n" : "=f"(r) : "f"(x));
  return r;
}

__device__ __forceinline__ int y_slot(int wg, int it) {
  return it == 0 ? OFF_T + T_A1 + wg * 2048 : OFF_U + wg * 4096 + (it == 3 ? 8192 : (it - 1) * 2048);
}

__device__ __forceinline__ void to_arr(uint32_t (&d)[4], uint4 v) { d[0] = v.x; d[1] = v.y; d[2] = v.z; d[3] = v.w; }

__device__ __forceinline__ void attn_stage(uint32_t sb, int blk, int lane, const float (&acc)[96], uint32_t (&k1)[2][4]) {
  const int lr = lane & 7, lm = lane >> 3;
  const uint32_t base = sb + OFF_VP + (blk * 16 + lr + 8 * (lm & 1)) * 128;
#pragma unroll
  for (int i = 0; i < 8; i++) k1[i >> 2][i & 3] = pack_bf16(acc[34 + 4 * i], acc[35 + 4 * i]);
  const uint32_t kh = sb + OFF_KH + blk * 2048 + lane * 16;
  sts128(kh, k1[0][0], k1[0][1], k1[0][2], k1[0][3]);
  sts128(kh + 512, k1[1][0], k1[1][1], k1[1][2], k1[1][3]);
#pragma unroll
  for (int j = 0; j < 8; j += 2)
    stsm4(base + (((j + (lm >> 1)) ^ lr) << 4), pack_bf16(acc[64 + 4 * j], acc[65 + 4 * j]),
          pack_bf16(acc[66 + 4 * j], acc[67 + 4 * j]), pack_bf16(acc[68 + 4 * j], acc[69 + 4 * j]),
          pack_bf16(acc[70 + 4 * j], acc[71 + 4 * j]));
}
__device__ __forceinline__ void attn_pack(const float (&acc)[96], uint32_t (&qa)[2][8], uint32_t (&k0)[2][4]) {
#pragma unroll
  for (int hd = 0; hd < 2; hd++) {
#pragma unroll
    for (int i = 0; i < 8; i++) {
      asm volatile("cvt.rn.bf16x2.f32 %0, %1, %2;\n" : "=r"(qa[hd][i]) : "f"(acc[16 * hd + 2 * i + 1]), "f"(acc[16 * hd + 2 * i]));
    }
#pragma unroll
    for (int i = 0; i < 4; i++) {
      asm volatile("cvt.rn.bf16x2.f32 %0, %1, %2;\n" : "=r"(k0[hd][i]) : "f"(acc[33 + 16 * hd + 4 * i]), "f"(acc[32 + 16 * hd + 4 * i]));
    }
  }
}
__device__ __forceinline__ void attn_own(const uint32_t (&k0)[2][4], const uint32_t (&k1)[2][4], bool le0, bool le1,
                                         const uint32_t (&qa)[2][8], float (&l)[2][4]) {
#pragma unroll
  for (int hd = 0; hd < 2; hd++) {
    float s0[4], s1[4];
    mma16816_z(s0, qa[hd][0], qa[hd][1], qa[hd][2], qa[hd][3], k0[hd][0], k0[hd][1]);
    mma16816_z(s1, qa[hd][0], qa[hd][1], qa[hd][2], qa[hd][3], k1[hd][0], k1[hd][1]);
    mma16816(s0, qa[hd][4], qa[hd][5], qa[hd][6], qa[hd][7], k0[hd][2], k0[hd][3]);
    mma16816(s1, qa[hd][4], qa[hd][5], qa[hd][6], qa[hd][7], k1[hd][2], k1[hd][3]);
    l[hd][0] = s0[0];
    l[hd][1] = s0[1];
    l[hd][2] = le0 ? s1[2] : s0[2];
    l[hd][3] = le1 ? s1[3] : s0[3];
  }
}
template <int N> __device__ __forceinline__ void quad_softmax(float (&x)[N][2], uint32_t (&pp)[N]) {
  const float c2 = 1.4426950408889634f;
  uint32_t q[N], mx[N / 2];
#pragma unroll
  for (int n = 0; n < N; n++) {
    const uint32_t r = pack_bf16(x[n][0], x[n][1]);
    q[n] = bfma2(r, 0x3e353e35u, bmul2(r, 0x379e379eu));
    x[n][0] = bf_lo(q[n]);
    x[n][1] = bf_hi(q[n]);
  }
#pragma unroll
  for (int n = 0; n < N / 2; n++)
    mx[n] = bmax2(__byte_perm(q[2 * n], q[2 * n + 1], 0x5410), __byte_perm(q[2 * n], q[2 * n + 1], 0x7632));
#pragma unroll
  for (int o = 1; o <= 2; o++)
#pragma unroll
    for (int n = 0; n < N / 2; n++) mx[n] = bmax2(mx[n], __shfl_xor_sync(0xffffffffu, mx[n], o));
  float m[N], t[N];
#pragma unroll
  for (int n = 0; n < N / 2; n++) {
    m[2 * n] = bf_lo(mx[n]);
    m[2 * n + 1] = bf_hi(mx[n]);
  }
#pragma unroll
  for (int n = 0; n < N; n++) {
    const float nm = -m[n] * c2;
    x[n][0] = ex2(fmaf(x[n][0], c2, nm));
    x[n][1] = ex2(fmaf(x[n][1], c2, nm));
    t[n] = x[n][0] + x[n][1];
  }
#pragma unroll
  for (int o = 1; o <= 2; o++)
#pragma unroll
    for (int n = 0; n < N; n++) t[n] += __shfl_xor_sync(0xffffffffu, t[n], o);
#pragma unroll
  for (int n = 0; n < N; n++) {
    const float inv = rcp(t[n]);
    pp[n] = pack_bf16(x[n][0] * inv, x[n][1] * inv);
  }
}
__device__ __forceinline__ void attn_pv(uint32_t dst, const uint32_t (&va)[4], const uint32_t (&vb)[4], uint32_t pp,
                                        uint32_t maskLE) {
  const uint32_t b0 = pp & ~maskLE, b1 = pp & maskLE;
  float oa[4], ob[4];
  mma16816_z(oa, va[0], va[1], va[2], va[3], b0, b1);
  mma16816_z(ob, vb[0], vb[1], vb[2], vb[3], b0, b1);
  stsm4t(dst, pack_bf16(oa[0], oa[1]), pack_bf16(oa[2], oa[3]), pack_bf16(ob[0], ob[1]), pack_bf16(ob[2], ob[3]));
}

template <int MODE>
__global__ void __cluster_dims__(2, 1, 1) __launch_bounds__(NTHREADS, 1)
fused_kernel(const Params p, const __grid_constant__ CUtensorMap tmX, const __grid_constant__ CUtensorMap tmW,
             const __grid_constant__ CUtensorMap tmWo,
             const __grid_constant__ CUtensorMap tmQ,
             const __grid_constant__ CUtensorMap tmXh, const __grid_constant__ CUtensorMap tmWh) {
  extern __shared__ __align__(1024) uint8_t smem[];
  const uint32_t sb = smem_u32(smem);
  const uint32_t bars = sb + OFF_BAR;
  const int tid = threadIdx.x, lane = tid & 31, warp = __shfl_sync(0xffffffffu, tid >> 5, 0);
  const int rank = blockIdx.x & 1;
  const bool halo_cta = blockIdx.x < 4;
  if (halo_cta && MODE != 0) return;
  int grp, mem;
  {
    const int t = (blockIdx.x >> 1) - 4, u = t - 32;
    const int q7 = (u * 37) >> 8;
    const bool lo = (unsigned)t < 32u, mid = (unsigned)u < 28u;
    grp = lo ? (t & 7) : (mid ? 1 + u - 7 * q7 : 0);
    mem = lo ? (t >> 3) : (mid ? 4 + q7 : (t < 0 ? t + 6 : t - 54));
  }
  const int rg = (grp >> 2) * 4 + (mem >> 1), hp = (grp & 3) * 4 + (mem & 1) * 2 + rank;
  const int rb2 = (grp >> 2) * 8 + mem, cb2 = (grp & 3) * 2 + rank;
  const int chb = grp * 16 + mem * 2 + rank;
  const int cta = rg * 16 + hp;
  const int par = rg >> 2, gidx = rg & 3;

  if (tid < 256 && !halo_cta && MODE != 2) {
    const int r = tid >> 3, c = tid & 7;
    const uint32_t so = r * 128 + ((c ^ (r & 7)) << 4);
    const __nv_bfloat16* wg0 = p.w + (size_t)r * (3 * DM) + hp * 64 + c * 8;
    const __nv_bfloat16* xg0 = p.x + (size_t)(2 * (gidx * 256 + r) + par) * DM + c * 8;
#pragma unroll
    for (int j = 0; j < 3; j++) cp_async16n(sb + OFF_1B + j * 4096 + so, wg0 + j * DM);
#pragma unroll
    for (int i = 0; i < 8; i++) cp_async16n(sb + i * 4096 + so, xg0 + (size_t)i * 64 * DM);
    asm volatile("cp.async.commit_group;\n" ::: "memory");
  }
  if (tid == 256) {
    prefetch_tmap(halo_cta ? &tmXh : &tmX);
#pragma unroll
    for (int i = 0; i < NS1B; i++) mbar_init(bars + 8 * (BAR_FULLB + i), 1);
#pragma unroll
    for (int i = 0; i < NS1A; i++) mbar_init(bars + 8 * (BAR_FULLA + i), 1);
    asm volatile("fence.mbarrier_init.release.cluster;\n" ::: "memory");
    if (!halo_cta && MODE != 2) {
      mbar_expect_tx(bars + 8 * (BAR_FULLB + 1), STG1B);
      tma_load_3d(sb + OFF_1B + 1 * STG1B, &tmW, bars + 8 * (BAR_FULLB + 1), hp * 64, 32, 0);
      mbar_expect_tx(bars + 8 * (BAR_FULLB + 2), STG1B);
      tma_load_3d(sb + OFF_1B + 2 * STG1B, &tmW, bars + 8 * (BAR_FULLB + 2), hp * 64, 64, 0);
    } else {
      prefetch_tmap(&tmWh);
    }
  } else if (tid == 288) {
#pragma unroll
    for (int i = 0; i < NS1A; i++) mbar_init(bars + 8 * (BAR_EMPTYA + i), 4);
#pragma unroll
    for (int i = 0; i < NS1B; i++) mbar_init(bars + 8 * (BAR_EMPTYB + i), 2);
    asm volatile("fence.mbarrier_init.release.cluster;\n" ::: "memory");
  } else if (tid == 320) {
#pragma unroll
    for (int i = 0; i < NS2; i++) {
      mbar_init(bars + 8 * (BAR_FULL2 + i), 1);
      mbar_init(bars + 8 * (BAR_EMPTY2 + i), 4);
    }
#pragma unroll
    for (int i = 0; i < 6; i++) mbar_init(bars + 8 * (BAR_QF + i), 1);
    asm volatile("fence.mbarrier_init.release.cluster;\n" ::: "memory");
  } else if (tid == 352) {
    mbar_init(bars + 8 * BAR_T, 1);
    mbar_init(bars + 8 * BAR_UH, 3);
    mbar_init(bars + 8 * BAR_LFREE, 4);
    mbar_init(bars + 8 * BAR_LAND, 1);
    mbar_init(bars + 8 * BAR_U, 1);
    mbar_init(bars + 8 * BAR_Q, 1);
    mbar_init(bars + 8 * (BAR_Q + 1), 1);
    mbar_init(bars + 8 * BAR_STG, 9);
    asm volatile("fence.mbarrier_init.release.cluster;\n" ::: "memory");
  }
  if (warp == 8) PROF2(23);
  cluster_sync_all();
  if (warp == 8) PROF2(24);

  if (warp >= 8) {
    const int hw = warp - 8;
    const int lr = lane & 7, lm = lane >> 3;
    auto g1_issue_a = [&](int j, int s) {
      const uint32_t fb = bars + 8 * (BAR_FULLA + s);
      mbar_expect_tx(fb, STG1A);
      tma_load_3d_mc(sb + s * STG1A + rank * 16384, &tmX, fb, j * 64, par, gidx * 256 + rank * 128);
    };
    auto g1_issue_b = [&](int kb, int s) {
      const uint32_t fb = bars + 8 * (BAR_FULLB + s);
      mbar_expect_tx(fb, STG1B);
      tma_load_3d(sb + OFF_1B + s * STG1B, &tmW, fb, hp * 64, kb * 32, 0);
    };
    asm volatile("setmaxnreg.dec.sync.aligned.u32 %0;\n" :: "n"(REG_HELP));

    if (halo_cta) {
      if (hw == 0) {
        int s = 0, ph = 1;
#pragma unroll 1
        for (int kb = 0; kb < 16; kb++) {
          mbar_wait(bars + 8 * (BAR_EMPTYB + s), ph);
          const uint32_t fb = bars + 8 * (BAR_FULLB + s), st = sb + s * STGH;
          if (elect_one()) {
            mbar_expect_tx(fb, STGH);
            tma_load_4d(st, &tmXh, fb, kb * 64, 248, 0, 0);
            tma_load_3d(st + 8192, &tmWh, fb, 0, kb * 64, 16 + blockIdx.x * 4);
            tma_load_3d(st + 8192 + 32768, &tmWh, fb, 0, kb * 64, 32 + blockIdx.x * 4);
          }
          if (++s == 3) { s = 0; ph ^= 1; }
        }
      }
      __syncwarp();
    } else if (hw == 0) {
      uint32_t epoch = 0;
      if (MODE == 2) {
        if (lane < NS2) mbar_arrive_cluster_n(mapa(bars, rank) + 8 * (BAR_EMPTY2 + lane), 4);
      } else {
      epoch = ld_relaxed(g_flag_o + 2 * cta) + 1;
      if (lane == 0) {
        mbar_expect_tx(bars + 8 * BAR_U, 32768);
        mbar_expect_tx(bars + 8 * BAR_LAND, 32768);
        mbar_expect_tx(bars + 8 * BAR_Q, 16384);
        mbar_expect_tx(bars + 8 * (BAR_Q + 1), 16384);
        mbar_expect_tx(bars + 8 * BAR_T, T_END);
      }
      {
        int sa = 1, pha = 1, sbb = 2, phb = 1;
#pragma unroll 1
        for (int kb = 2; kb < 32; kb++) {
          if (!(kb & 1)) {
            mbar_wait(bars + 8 * (BAR_EMPTYA + sa), pha);
            if (elect_one()) g1_issue_a(kb >> 1, sa);
            if (++sa == NS1A) { sa = 0; pha ^= 1; }
          }
          mbar_wait(bars + 8 * (BAR_EMPTYB + sbb), phb);
          if (kb > 2 && elect_one()) g1_issue_b(kb, sbb);
          __syncwarp();
          if (kb == 4) PROF2(27);
          if (kb == 1) PROF2(38);
          if (kb == 2) PROF2(39);
          if (++sbb == NS1B) { sbb = 0; phb ^= 1; }
        }
      }
      static_assert(32 % NS1B == 2 && (32 / NS1B) % 2 == 0, "slots / parity of the constant loads");
      const uint8_t* tab = reinterpret_cast<const uint8_t*>(g_tab);
      if (lane == 0) {
        prefetch_tmap(&tmWo);
        prefetch_tmap(&tmQ);
        bulk_load(sb + OFF_T + T_A1, tab + T_A1, T_END - T_A1, bars + 8 * BAR_T);
        mbar_wait(bars + 8 * (BAR_EMPTYB + 2), 1);
        bulk_load(sb + OFF_T, tab, T_A1 - 2 * STG1B, bars + 8 * BAR_T);
        if (gidx != 0) wait_flag(g_flag_h + (hp >> 2), epoch);
      }
      __syncwarp();
      {
        uint4 hk0 = make_uint4(0, 0, 0, 0), hk1 = hk0, hv0 = hk0, hv1 = hk0;
        if (gidx != 0) {
          const uint4* src = g_halo + cta * 128 + lane;
          hk0 = __ldcg(src); hk1 = __ldcg(src + 32); hv0 = __ldcg(src + 64); hv1 = __ldcg(src + 96);
        }
        if (lane == 0) {
          mbar_wait(bars + 8 * (BAR_EMPTYB + 3), 1);
          bulk_load(sb + OFF_T + T_A1 - 2 * STG1B, tab + T_A1 - 2 * STG1B, STG1B, bars + 8 * BAR_T);
        }
        __syncwarp();
        PROF2(18);
        sts128(sb + OFF_L0 + 1024 + lane * 16, hk0.x, hk0.y, hk0.z, hk0.w);
        sts128(sb + OFF_L0 + 1536 + lane * 16, hk1.x, hk1.y, hk1.z, hk1.w);
        stsm4(sb + OFF_L0 + lr * 128 + ((lm ^ lr) << 4), hv0.x, hv0.y, hv0.z, hv0.w);
        stsm4(sb + OFF_L0 + lr * 128 + (((4 + lm) ^ lr) << 4), hv1.x, hv1.y, hv1.z, hv1.w);
        __syncwarp();
        if (lane == 0) {
          mbar_arrive(bars + 8 * BAR_STG);
          mbar_wait(bars + 8 * (BAR_EMPTYB + 4), 1);
          bulk_load(sb + OFF_T + T_A1 - STG1B, tab + T_A1 - STG1B, STG1B, bars + 8 * BAR_T);
        }
        __syncwarp();
      }
      }
      if (MODE != 1) {
#pragma unroll 1
        for (int kb = 0; kb < NS2; kb++) {
          mbar_wait(bars + 8 * (BAR_EMPTY2 + kb), 0);
          if (elect_one()) {
            mbar_expect_tx(bars + 8 * (BAR_FULL2 + kb), STG2);
            tma_load_3d(sb + kb * STG2 + 16384, &tmWo, bars + 8 * (BAR_FULL2 + kb), 0, kb * 64, cb2 * 2);
          }
        }
        PROF2(20);
        const __nv_bfloat16* osrc = g_o + (size_t)(rb2 >> 1) * 16 * 16384 + ((rb2 & 1) * 2 + rank) * 4096;
        const uint32_t* flag = g_flag_o + (rb2 >> 1) * 32 + (lane & 15) * 2 + (rb2 & 1);
        uint32_t ready = MODE == 0 ? 0u : ~0u;
#pragma unroll 1
        for (int kb = 0; kb < 16; kb++) {
          const int s = kb & (NS2 - 1);
          const uint32_t fb = bars + 8 * (BAR_FULL2 + s);
          const uint32_t st = sb + s * STG2;
          if (!((ready >> kb) & 1)) {
            int n = 0;
            do {
              ready = __ballot_sync(0xffffffffu, ld_acquire(flag) == epoch);
            } while (!((ready >> kb) & 1) && ++n < SPIN_LIMIT);
            fence_async_all();
          }
          if (kb == 0) PROF(21);
          if (kb >= NS2) mbar_wait(bars + 8 * (BAR_EMPTY2 + s), (kb >> 2) & 1);
          if (elect_one()) {
            if (kb >= NS2) mbar_expect_tx(fb, STG2);
            asm volatile(
                "cp.async.bulk.shared::cluster.global.mbarrier::complete_tx::bytes.multicast::cluster [%0], [%1], %2, [%3], %4;\n"
                ::"r"(st + rank * 8192), "l"(osrc), "r"(8192), "r"(fb), "h"((uint16_t)3) : "memory");
            if (kb >= NS2) tma_load_3d(st + 16384, &tmWo, fb, 0, kb * 64, cb2 * 2);
          }
          if (kb == 3) PROF(37);
          osrc += 16384;
        }
      }
      __syncwarp();
    } else if (MODE != 2) {
      {
        const int g = lane >> 2, t = lane & 3;
        uint32_t w[2][4];
#pragma unroll
        for (int h = 0; h < 2; h++) {
          const uint2 x = __ldg(reinterpret_cast<const uint2*>(p.shift_k + ((chb & ~1) * 8 + h * 8 + g) * 4));
          w[h][0] = __byte_perm(x.x, x.x, 0x1010);
          w[h][1] = __byte_perm(x.x, x.x, 0x3232);
          w[h][2] = __byte_perm(x.y, x.y, 0x1010);
          w[h][3] = __byte_perm(x.y, x.y, 0x3232);
        }
        auto swz = [](int r) { return (((r & 29) | ((r ^ (r >> 2)) & 2)) << 5) | (r & 16); };
        const uint32_t kring = sb + OFF_H + (hw - 1) * 8192, vring = kring + 4096;
        const int s0 = rank * 32 + (hw - 1) * 11, s1 = hw == 3 ? rank * 32 + 32 : s0 + 11;
        const size_t goff = (size_t)(lane >> 1) * DM + (chb & ~1) * 8 + (lane & 1) * 8;
        const __nv_bfloat16* kg = p.k + goff;
        const __nv_bfloat16* vg = p.v + goff;
        const uint32_t d0 = swz(lane >> 1) ^ ((lane & 1) << 4), d1 = swz(16 + (lane >> 1)) ^ ((lane & 1) << 4);
        auto issue = [&](int st) {
          const uint32_t so = (st & 3) << 10;
          cp_async16(kring + so + d0, kg + (size_t)st * 32 * DM, 16);
          cp_async16(kring + so + d1, kg + (size_t)(st * 32 + 16) * DM, 16);
          cp_async16(vring + so + d0, vg + (size_t)st * 32 * DM, 16);
          cp_async16(vring + so + d1, vg + (size_t)(st * 32 + 16) * DM, 16);
        };
        const int xa = 8 * (lr >> 1) + 2 * lm + (lr & 1), xb = 8 * (lr >> 1) - 4 + 2 * (lm & 1) + (lr & 1);
        const uint32_t la = swz(xa), lb = swz(xb & 31);
        const int backb = xb < 0 ? 1 : 0;
        const uint32_t ud[2] = {mapa(sb + OFF_U + g * 4096 + t * 16, 0), mapa(sb + OFF_U + g * 4096 + t * 16, 1)};
        const uint32_t ub[2] = {mapa(bars + 8 * BAR_U, 0), mapa(bars + 8 * BAR_U, 1)};
        if (lane == 0) mbar_wait(bars + 8 * (BAR_FULLB + NS1B - 1), 0);
        __syncwarp();
        if (lane >= 24) cp_async16(kring + (((s0 - 1) & 3) << 10) + d1, s0 > 0 ? kg + (size_t)(s0 * 32 - 16) * DM : kg, s0 > 0 ? 16 : 0);
        issue(s0);
        asm volatile("cp.async.commit_group;\n" ::: "memory");
        issue(s0 + 1);
        asm volatile("cp.async.commit_group;\n" ::: "memory");
#pragma unroll 1
        for (int st = s0; st < s1; st++) {
          if (st + 2 < s1) issue(st + 2);
          if (hw == 1 && st - s0 < 8) prefetch_l2(p.ssm_k + (size_t)(chb * 8 + st - s0) * SEQ + lane * 64);
          if (hw == 2 && st == s0 + 4 && lane < 3 && chb * 3 + lane < T_END / 128) prefetch_l2(g_tab + (chb * 3 + lane) * 32);
          const uint32_t uo = (st ^ ((g ^ (st >> 2)) & 1)) * 64;
          asm volatile("cp.async.commit_group;\n" ::: "memory");
          asm volatile("cp.async.wait_group 2;\n" ::: "memory");
          __syncwarp();
#pragma unroll
          for (int h = 0; h < 2; h++) {
            uint32_t e[6], vv[4], e4[4];
            ldsm4t(e4, kring + ((st & 3) << 10) + (la ^ (h << 4)));
            ldsm2t(e[0], e[1], kring + (((st - backb) & 3) << 10) + (lb ^ (h << 4)));
            ldsm4t(vv, vring + ((st & 3) << 10) + (la ^ (h << 4)));
            e[2] = e4[0]; e[3] = e4[1]; e[4] = e4[2]; e[5] = e4[3];
            uint32_t o[5];
#pragma unroll
            for (int i = 0; i < 5; i++) o[i] = __byte_perm(e[i], e[i + 1], 0x5432);
#pragma unroll
            for (int i = 0; i < 4; i++) {
              uint32_t a = bmul2(o[i], w[h][3]);
              a = bfma2(e[i + 1], w[h][2], a);
              a = bfma2(o[i + 1], w[h][1], a);
              a = bfma2(e[i + 2], w[h][0], a);
              vv[i] = bmul2(a, vv[i]);
            }
            st_async128(ud[h] + uo, ub[h], vv[0], vv[1], vv[2], vv[3]);
          }
          __syncwarp();
        }
        PROF(16);
        nb_sync(NB_HELP3, 96);
      }
      {
        const int rw = (lane >> 3) + (lane & 4), ck = lane & 3;
        const uint32_t so = rw * 64 + ck * 16, dof = rw * 128 + ((ck ^ rw) << 4);
        auto store = [&](uint32_t dst, const uint32_t (&x)[32]) {
#pragma unroll
          for (int i = 0; i < 8; i++)
            sts128(dst + ((dof + (i & 3) * 1024) ^ ((i >> 2) << 6)), x[4 * i], x[4 * i + 1], x[4 * i + 2], x[4 * i + 3]);
        };
#pragma unroll 1
        for (int c = hw - 1; c < 8; c += 3) {
          uint32_t x[32];
          const uint8_t* src = reinterpret_cast<const uint8_t*>(p.ssm_k + (size_t)(chb * 8 + c) * SEQ) + so;
#pragma unroll
          for (int i = 0; i < 8; i++) {
            const uint4 v = __ldg(reinterpret_cast<const uint4*>(src + i * 512));
            x[4 * i] = v.x; x[4 * i + 1] = v.y; x[4 * i + 2] = v.z; x[4 * i + 3] = v.w;
          }
          const float h0 = bf_lo(x[0]) + (lane == 0 ? __bfloat162float(p.ssm_D[chb * 8 + c]) : 0.f), h1 = bf_hi(x[0]);
          x[0] = pack_bf16(h0, h1);
          const uint32_t e = to_fp16(x);
          const float sc = __uint_as_float((259u - e) << 23);
          asm("cvt.rn.f16x2.f32 %0, %1, %2;\n" : "=r"(x[0]) : "f"(h1 * sc), "f"(h0 * sc));
          store(sb + OFF_H + c * 4096, x);
          if (lane == 0) asm volatile("st.shared.u32 [%0], %1;\n" ::"r"(sb + OFF_SC + c * 4), "r"(e) : "memory");
          prefetch_l2(p.q + (size_t)chb * 16384 + c * 2048 + lane * 64);
          if (lane < 16) prefetch_l2(p.wo + (size_t)chb * 8192 + c * 1024 + lane * 64);
        }
        PROF(19);
        mbar_wait(bars + 8 * BAR_U, 0);
#pragma unroll 1
        for (int c = hw - 1; c < 8; c += 3) {
          uint32_t x[32];
          const uint32_t src = sb + OFF_U + c * 4096 + (so ^ (((c ^ (lane >> 2)) & 1) << 6));
#pragma unroll
          for (int i = 0; i < 8; i++) {
            const uint4 v = lds128(src + i * 512);
            x[4 * i] = v.x; x[4 * i + 1] = v.y; x[4 * i + 2] = v.z; x[4 * i + 3] = v.w;
          }
          const int e = to_fp16(x);
          store(sb + OFF_U + c * 4096, x);
          if (lane == 0) {
            const int f = min(max(e + (int)lds32(sb + OFF_SC + c * 4) - 129, 0), 254);
            asm volatile("st.shared.u32 [%0], %1;\n" ::"r"(sb + OFF_SC + c * 4), "r"(f << 23) : "memory");
          }
        }
        fence_async_smem();
        __syncwarp();
        if (lane == 0) mbar_arrive(bars + 8 * BAR_UH);
        PROF(32);
      }
      if (hw < 3) {
        const uint32_t rb = mapa(bars, lane & 1);
        const uint32_t epoch = ld_relaxed(g_flag_o + 2 * cta + hw - 1) + 1;
        nb_sync(NB_OREADY + hw - 1, 160);
        if (lane == 0) {
          asm volatile("cp.async.bulk.global.shared::cta.bulk_group [%0], [%1], %2;\n" ::"l"(g_o + (size_t)cta * 16384 + (hw - 1) * 8192),
                       "r"(sb + OFF_OP + (hw - 1) * 16384), "r"(16384) : "memory");
          bulk_commit();
        }
        if (lane < 2) {
          mbar_arrive_cluster(rb + 8 * (BAR_EMPTY2 + 0));
          mbar_arrive_cluster(rb + 8 * (BAR_EMPTY2 + 1));
        }
        if (lane == 0) asm volatile("cp.async.bulk.wait_group.read 0;\n" ::: "memory");
        __syncwarp();
        if (lane < 2) mbar_arrive_cluster(rb + 8 * (BAR_EMPTY2 + 2));
        if (lane == 0) {
          bulk_wait0();
          st_release(g_flag_o + 2 * cta + hw - 1, epoch);
        }
        __syncwarp();
        PROF(17);
      } else {
#pragma unroll 1
        for (int pc = 0; pc < 6; pc++) {
          mbar_wait(bars + 8 * (BAR_QF + pc), 0);
          if (elect_one()) {
            tma_load_2d(sb + OFF_H + pc * 4096, &tmQ, bars + 8 * (BAR_Q + (pc >> 2)), (chb & ~1) * 8, rank * 1024 + pc * 128);
            if (pc >= 4) tma_load_2d(sb + OFF_U + pc * 4096, &tmQ, bars + 8 * (BAR_Q + 1), (chb & ~1) * 8, rank * 1024 + (pc + 2) * 128);
          }
        }
        __syncwarp();
      }
      {
        const int c8 = (4 * (lr >> 1) + 2 * (lm & 1) + (lr & 1)) & 7;
        const bool own = (lr >> 2) == rank;
        const uint32_t ya = sb + (own ? y_slot(c8 & 1, c8 >> 1) : OFF_LAND + c8 * 2048);
        const uint32_t yx = ((lm >> 1) ^ lr) << 4;
        const int row = (lane >> 4) * 16 + ((lane >> 2) & 3);
        uint2* og = reinterpret_cast<uint2*>(p.out + (size_t)(rank * 1024 + row) * (2 * DM) + (chb & ~1) * 8 + (lane & 3) * 4);
        const uint32_t qa = sb + OFF_H + row * 32 + (lane & 3) * 8;
        mbar_wait(bars + 8 * BAR_Q, 0);
        mbar_wait(bars + 8 * BAR_LAND, 0);
        PROF(33);
#pragma unroll 1
        for (int j = hw - 1; j < 16; j += 3) {
          uint32_t y[4][4];
          uint2 q[8];
          if (j >= 8) mbar_wait(bars + 8 * (BAR_Q + 1), 0);
          const uint32_t qj = qa + j * 2048 - (j >= 12 ? OFF_H - OFF_U + 8192 : 0);
#pragma unroll
          for (int i = 0; i < 4; i++) ldsm4t(y[i], ya + j * 128 + (yx ^ (i << 5)));
#pragma unroll
          for (int i = 0; i < 8; i++) q[i] = lds64(qj + (i >> 2) * 1024 + (i & 3) * 128);
#pragma unroll
          for (int i = 0; i < 8; i++)
            og[(size_t)(j * 64 + (i >> 2) * 32 + (i & 3) * 4) * (2 * DM / 4)] =
                make_uint2(bmul2(q[i].x, y[i >> 1][2 * (i & 1)]), bmul2(q[i].y, y[i >> 1][2 * (i & 1) + 1]));
        }
      }
      PROF(22);
    }
    cluster_sync_all();
  } else {
    asm volatile("setmaxnreg.inc.sync.aligned.u32 %0;\n" :: "n"(REG_MATH));
    if (warp == 0) PROF2(26);
    const int wg = warp >> 2;
    const int wtid = tid & 127;
    const bool signaller = (wtid == 0) || (wtid == 32);
    const uint32_t rbars = mapa(bars, wtid >> 5 & 1);

    if (halo_cta) {
      const uint32_t epoch = ld_relaxed(g_flag_h + blockIdx.x) + 1;
      float acc0[64], acc1[64];
      int s = 0, ph = 0;
#pragma unroll 1
      for (int kb = 0; kb < 16; kb++) {
        mbar_wait(bars + 8 * (BAR_FULLB + s), ph);
        const uint32_t st = sb + s * STGH;
        const uint64_t da = mkdesc(st, 16, 1024, 1);
        const uint64_t db = mkdesc(st + 8192 + wg * 32768, 8192, 1024, 1);
        wg_fence();
#pragma unroll
        for (int kk = 0; kk < 4; kk++) {
          wgmma_n128(acc0, da + 2 * kk, db + 128 * kk, kb + kk);
          wgmma_n128(acc1, da + 2 * kk, db + 1024 + 128 * kk, kb + kk);
        }
        wg_commit();
        wg_wait<0>();
        if (wtid == 0) mbar_arrive(bars + 8 * (BAR_EMPTYB + s));
        if (++s == 3) { s = 0; ph ^= 1; }
      }
      fence_regs(acc0);
      fence_regs(acc1);
      if ((warp & 3) != 3) {
#pragma unroll
        for (int hh = 0; hh < 2; hh++) {
          uint4* dst = g_halo + ((hh * 4 + (warp & 3) + 1) * 16 + blockIdx.x * 4) * 128 + wg * 64 + lane;
#pragma unroll
          for (int j = 0; j < 4; j++) {
            const int o = 16 * j + 2 * hh;
            dst[(j >> 1) * 128 + (j & 1) * 32] =
                make_uint4(pack_bf16(acc0[o], acc0[o + 1]), pack_bf16(acc0[o + 4], acc0[o + 5]),
                           pack_bf16(acc0[o + 8], acc0[o + 9]), pack_bf16(acc0[o + 12], acc0[o + 13]));
            dst[(2 + (j >> 1)) * 128 + (j & 1) * 32] =
                make_uint4(pack_bf16(acc1[o], acc1[o + 1]), pack_bf16(acc1[o + 4], acc1[o + 5]),
                           pack_bf16(acc1[o + 8], acc1[o + 9]), pack_bf16(acc1[o + 12], acc1[o + 13]));
          }
        }
      }
      nb_sync(NB_G1DONE, 256);
      if (tid == 0) st_release(g_flag_h + blockIdx.x, epoch);
      PROF(36);
      cluster_sync_all();
      return;
    }

    if (MODE != 2) {
    {
      float acc0[96], acc1[96];
      int sa = 0, pha = 0, sbb = 0, phb = 0;
      asm volatile("cp.async.wait_group 0;\n" ::: "memory");
      fence_async_smem();
      nb_sync(NB_FIRST, 256);
      if (tid == 0) {
        mbar_arrive(bars + 8 * BAR_FULLA);
        mbar_arrive(bars + 8 * BAR_FULLB);
      }
      PROF(0 + wg);
#pragma unroll 1
      for (int kb = 0; kb < 30; kb++) {
        if (!(kb & 1)) mbar_wait(bars + 8 * (BAR_FULLA + sa), pha);
        mbar_wait(bars + 8 * (BAR_FULLB + sbb), phb);
        if (kb == 0) PROF2(0 + wg);
        if (kb == 4 && wg == 0) PROF2(28);
        if (kb == 8 && wg == 0) PROF2(29);
        if (kb == 16 && wg == 0) PROF2(30);
        const uint64_t da = mkdesc(sb + sa * STG1A + wg * 16384 + (kb & 1) * 64, 16, 1024, 1);
        const uint64_t db = mkdesc(sb + OFF_1B + sbb * STG1B, 4096, 1024, 1);
        wg_fence();
        wgmma_n192(acc0, da, db, kb);
        wgmma_n192(acc1, da + 512, db, kb);
        wgmma_n192(acc0, da + 2, db + 128, 1);
        wgmma_n192(acc1, da + 514, db + 128, 1);
        wg_commit();
        wg_wait<1>();
        if (kb > 0) {
          if (wtid == 64) mbar_arrive(bars + 8 * (BAR_EMPTYB + (sbb == 0 ? NS1B - 1 : sbb - 1)));
          if (!(kb & 1) && signaller) mbar_arrive_cluster(rbars + 8 * (BAR_EMPTYA + (sa == 0 ? NS1A - 1 : sa - 1)));
        }
        if (++sbb == NS1B) { sbb = 0; phb ^= 1; }
        if ((kb & 1) && ++sa == NS1A) { sa = 0; pha ^= 1; }
      }
      const int blk0 = wg * 8 + (warp & 3);
      const int lr = lane & 7, lm = lane >> 3;
      const bool le0 = 2 * (lane & 3) <= (lane >> 2), le1 = 2 * (lane & 3) + 1 <= (lane >> 2);
      const uint32_t maskLE = (le0 ? 0x0000FFFFu : 0u) | (le1 ? 0xFFFF0000u : 0u);
      uint32_t k0[2][2][4], k1[2][2][4], qa[2][2][8];
      float l[2][2][4];
      {
        static_assert(15 % NS1A == 0 && 30 % NS1B == 0, "slots of the last k blocks");
        mbar_wait(bars + 8 * BAR_FULLA, 1);
        mbar_wait(bars + 8 * BAR_FULLB, 0);
        mbar_wait(bars + 8 * (BAR_FULLB + 1), 0);
        const uint64_t da = mkdesc(sb + wg * 16384, 16, 1024, 1);
        const uint64_t db = mkdesc(sb + OFF_1B, 4096, 1024, 1);
        wg_fence();
#pragma unroll
        for (int i = 0; i < 4; i++) wgmma_n192(acc0, da + 2 * i, db + (i >> 1) * (STG1B >> 4) + (i & 1) * 128, 1);
        wg_commit();
        wg_wait<1>();
        if (wtid == 64) mbar_arrive(bars + 8 * (BAR_EMPTYB + NS1B - 1));
#pragma unroll
        for (int i = 0; i < 2; i++) wgmma_n192(acc1, da + 512 + 2 * i, db + (i >> 1) * (STG1B >> 4) + (i & 1) * 128, 1);
        wg_commit();
        wg_wait<1>();
        fence_regs(acc0);
        attn_stage(sb, blk0, lane, acc0, k1[0]);
#pragma unroll
        for (int i = 2; i < 4; i++) wgmma_n192(acc1, da + 512 + 2 * i, db + (i >> 1) * (STG1B >> 4) + (i & 1) * 128, 1);
        wg_commit();
        attn_pack(acc0, qa[0], k0[0]);
        wg_wait<0>();
        fence_regs(acc1);
      }
      PROF(2 + wg);
      attn_stage(sb, blk0 + 4, lane, acc1, k1[1]);
      __syncwarp();
      if (lane == 0) mbar_arrive(bars + 8 * BAR_STG);
      mbar_wait(bars + 8 * BAR_UH, 0);
      attn_pack(acc1, qa[1], k0[1]);
      attn_own(k0[0], k1[0], le0, le1, qa[0], l[0]);
      attn_own(k0[1], k1[1], le0, le1, qa[1], l[1]);
      const uint32_t cho[2] = {(uint32_t)(((lm & 1) ^ lr) << 4), (uint32_t)(((2 + (lm & 1)) ^ lr) << 4)};
      const uint32_t obase = sb + OFF_OP + (blk0 * 16 + lr) * 128;
      mbar_wait(bars + 8 * BAR_STG, 0);
      {
        uint32_t km[4][4], va[8][4], vb[8][4], pp[8];
        float x[8][2];
#pragma unroll
        for (int n = 0; n < 4; n++) {
          const int blk = blk0 + 4 * (n >> 1);
          to_arr(km[n], lds128(sb + (blk == 0 ? OFF_L0 + 1024 : OFF_KH + (blk - 1) * 2048) + (n & 1) * 512 + lane * 16));
        }
#pragma unroll
        for (int n = 0; n < 8; n++) {
          const int vr = (blk0 + 4 * ((n >> 1) & 1)) * 16 - 8 + 8 * (n >> 2) + 8 * (lm >> 1);
          const uint32_t vrow = sb + (vr < 0 ? OFF_L0 : OFF_VP + vr * 128) + lr * 128;
          ldsm4t(va[n], vrow + (cho[0] ^ ((n & 1) << 6)));
          ldsm4t(vb[n], vrow + (cho[1] ^ ((n & 1) << 6)));
        }
        const bool first = blk0 == 0 && gidx == 0;
#pragma unroll
        for (int n = 0; n < 4; n++) {
          const uint32_t(&q)[8] = qa[n >> 1][n & 1];
          float sm[4];
          mma16816_z(sm, q[0], q[1], q[2], q[3], km[n][0], km[n][1]);
          mma16816(sm, q[4], q[5], q[6], q[7], km[n][2], km[n][3]);
          if (n < 2 && first) sm[0] = sm[1] = -1e9f / 0.17677669529663687f;
          x[n][0] = le0 ? l[n >> 1][n & 1][0] : sm[0];
          x[n][1] = le1 ? l[n >> 1][n & 1][1] : sm[1];
          x[4 + n][0] = l[n >> 1][n & 1][2];
          x[4 + n][1] = l[n >> 1][n & 1][3];
        }
        quad_softmax<8>(x, pp);
#pragma unroll
        for (int n = 7; n >= 0; n--)
          attn_pv(obase + ((n >> 1) & 1) * 8192 + (n >> 2) * 1024 + (((4 * (n & 1) + lm) ^ lr) << 4), va[n], vb[n], pp[n],
                  maskLE);
      }
      fence_async_smem();
      nb_arrive(NB_OREADY + wg, 160);
    }

    {
      const int w = warp & 3;
      uint32_t a1[2][4], a4[8][4], tw[16], d1[32];
      float d4[16];
      const uint32_t tb = sb + OFF_T + wtid * 16;
      PROF(34 + wg);
      mbar_wait(bars + 8 * BAR_T, 0);
      to_arr(a1[0], lds128(tb + T_A1));
      to_arr(a1[1], lds128(tb + T_A1 + 2048));
      const uint64_t dx = mkdesc(sb + OFF_U + wg * 4096, OFF_H - OFF_U, 1024, 1);
      const uint64_t dz = mkdesc(sb + OFF_U + wg * 4096, 512, 128, 0);
      const uint64_t db2 = mkdesc(sb + OFF_T + T_B2, 128, 256, 0), db3 = mkdesc(sb + OFF_T + T_B3, 128, 256, 0);
      wg_fence();
      hmma_n128t<0>(d1, a1[0], dx);
      hmma_n128t<1>(d1, a1[1], dx + 128);
      wg_commit();
      auto ldtw = [&](int i) {
        const uint4 v = lds128(tb + T_TW + i * 2048);
        tw[4 * i] = v.x; tw[4 * i + 1] = v.y; tw[4 * i + 2] = v.z; tw[4 * i + 3] = v.w;
      };
      ldtw(0);
      ldtw(1);
      const uint32_t za = sb + (w < 2 ? OFF_U : OFF_H) + wg * 4096 + (w & 1) * 2048 + lane * 16;
      const uint32_t yl = (wtid ^ (4 * rank + wg)) * 16;
      const uint32_t yown = mapa(sb, rank) + yl, yrem = mapa(sb + OFF_LAND + wg * 2048, rank ^ 1) + yl;
      const uint32_t yb[2] = {mapa(bars + 8 * BAR_LAND, 0), mapa(bars + 8 * BAR_LAND, 1)};
      wg_wait<0>();
      fence_regs(d1);
      nb_sync(NB_WG + wg, 128);
      auto s4 = [&](int it) {
        wg_fence();
#pragma unroll
        for (int ks = 0; ks < 8; ks++) {
          const uint64_t d = dz + it * 512 + (ks & 3) * 64 + (ks >> 2) * ((OFF_H - OFF_U) >> 4);
          if (ks == 0) fmma_n32t<0>(d4, a4[ks], d);
          else fmma_n32t<1>(d4, a4[ks], d);
        }
        wg_commit();
      };
      auto e4 = [&](int it) {
        fence_regs(d4);
        const float sc = __uint_as_float(lds32(sb + OFF_SC + wg * 4 + it * 8));
        uint32_t r[8];
#pragma unroll
        for (int i = 0; i < 8; i++) r[i] = pack_bf16(d4[2 * i] * sc, d4[2 * i + 1] * sc);
        const uint32_t o = (yown + y_slot(wg, it)) ^ ((it >> 1) << 5), m = (yrem + it * 4096) ^ ((it >> 1) << 5);
        if (it == 0) mbar_wait(bars + 8 * BAR_LFREE, 0);
        st_async128(rank ? m : o, yb[0], r[0], r[2], r[1], r[3]);
        st_async128(rank ? o : m, yb[1], r[4], r[6], r[5], r[7]);
      };
#pragma unroll
      for (int it = 0; it < 4; it++) {
        if (it > 0) s4(it - 1);
        uint32_t a2[2][2][2][4], a3[2][2][4], d2[2][2][8], d3[2][8];
        fft_e1<0>(d1, tw, a2[0]);
        wg_fence();
#pragma unroll
        for (int c = 0; c < 4; c++) hmma_n32<0, 0>(d2[c & 1][c >> 1], a2[0][c & 1][c >> 1], db2 + (c >> 1) * 128);
        fft_e1<1>(d1, tw, a2[1]);
        wg_fence();
#pragma unroll
        for (int c = 0; c < 4; c++) {
          hmma_n32<1, 0>(d2[c & 1][c >> 1], a2[1][c & 1][c >> 1], db2 + (c >> 1) * 128 + 64);
          if (c & 1) wg_commit();
        }
        if (it > 0) {
          wg_wait<2>();
          e4(it - 1);
        } else {
          ldtw(2);
          ldtw(3);
#pragma unroll
          for (int i = 0; i < 8; i++) to_arr(a4[i], lds128(tb + T_A4 + i * 2048));
        }
        wg_wait<1>();
        fence_regs(d2[0][0]);
        fence_regs(d2[1][0]);
        fft_e2<0, 0>(d2[0][0], d2[1][0], a3[0]);
        fft_e2<0, 1>(d2[0][0], d2[1][0], a3[1]);
        wg_wait<0>();
        fence_regs(d2[0][1]);
        fence_regs(d2[1][1]);
        fft_e2<1, 0>(d2[0][1], d2[1][1], a3[0]);
        wg_fence();
        hmma_n32<0, 0>(d3[0], a3[0][0], db3);
        hmma_n32<0, 0>(d3[1], a3[0][1], db3);
        fft_e2<1, 1>(d2[0][1], d2[1][1], a3[1]);
        wg_fence();
        hmma_n32<1, 0>(d3[0], a3[1][0], db3 + 64);
        hmma_n32<1, 0>(d3[1], a3[1][1], db3 + 64);
        wg_commit();
        if (it < 3) {
          hmma_n128t<0>(d1, a1[0], dx + (it + 1) * 512);
          hmma_n128t<1>(d1, a1[1], dx + (it + 1) * 512 + 128);
          wg_commit();
          wg_wait<1>();
        } else {
          wg_wait<0>();
        }
        fence_regs(d3[0]);
        fence_regs(d3[1]);
        fft_e3(d3, tw, za + it * 8192);
        fence_async_smem();
        wg_wait<0>();
        fence_regs(d1);
        nb_sync(NB_WG + wg, 128);
        if (it == 0) {
          if (signaller) {
            mbar_arrive_cluster(rbars + 8 * BAR_LFREE);
            mbar_arrive_cluster(rbars + 8 * (BAR_EMPTY2 + 3));
          }
        } else if (wtid == 64) {
          mbar_arrive(bars + 8 * (BAR_QF + 2 * (it - 1)) + 8 * wg);
        }
        if (w == 0) PROF3(40 + 4 * wg + it);
      }
      s4(3);
      wg_wait<0>();
      e4(3);
      PROF(6 + wg);
    }
    }

    if (MODE != 1) {
      float acc[64];
#pragma unroll 1
      for (int kb = 0; kb < 16; kb++) {
        const int s = kb & (NS2 - 1);
        mbar_wait(bars + 8 * (BAR_FULL2 + s), (kb >> 2) & 1);
        if (kb == 0) PROF(8 + wg);
        if (warp == 4) PROF2(40 + kb);
        const uint32_t st = sb + s * STG2;
        const uint64_t da = mkdesc(st + wg * 8192, 16, 1024, 1);
        const uint64_t db = mkdesc(st + 16384, 8192, 1024, 1);
        wg_fence();
        wgmma_n128(acc, da, db, kb);
        wgmma_n128(acc, da + 2, db + 128, 1);
        wgmma_n128(acc, da + 4, db + 256, 1);
        wgmma_n128(acc, da + 6, db + 384, 1);
        wg_commit();
        wg_wait<0>();
        if (kb < 16 - NS2 && signaller) mbar_arrive_cluster(rbars + 8 * (BAR_EMPTY2 + s));
      }
      wg_wait<0>();
      fence_regs(acc);
      PROF(10 + wg);
      const int lr = lane & 7, lm = lane >> 3;
      const uint32_t wbase = sb + warp * 2048;
      const uint32_t base = wbase + (lr + 8 * (lm & 1)) * 128;
#pragma unroll
      for (int j = 0; j < 16; j += 2) {
        const uint32_t a = base + (j >> 3) * STG2 + ((((j & 7) + (lm >> 1)) ^ lr) << 4);
        stsm4(a, pack_bf16(acc[4 * j], acc[4 * j + 1]), pack_bf16(acc[4 * j + 2], acc[4 * j + 3]),
              pack_bf16(acc[4 * j + 4], acc[4 * j + 5]), pack_bf16(acc[4 * j + 6], acc[4 * j + 7]));
      }
      __syncwarp();
      {
        const int rr = lane >> 4, ck = lane & 7, hf = (lane >> 3) & 1;
        uint4* og = reinterpret_cast<uint4*>(p.out + (size_t)(2 * ((rb2 & 7) * 128 + warp * 16 + rr) + (rb2 >> 3)) * (2 * DM) + DM + cb2 * 128 + hf * 64 + ck * 8);
        uint4 v[8];
#pragma unroll
        for (int i = 0; i < 8; i++) v[i] = lds128(wbase + hf * STG2 + (2 * i + rr) * 128 + ((ck ^ ((2 * i + rr) & 7)) << 4));
#pragma unroll
        for (int i = 0; i < 8; i++) og[(size_t)i * 4 * (2 * DM / 8)] = v[i];
      }
      PROF(12 + wg);
    }
    cluster_sync_all();
  }
}

typedef CUresult (*EncodeFn)(CUtensorMap*, CUtensorMapDataType, cuuint32_t, void*, const cuuint64_t*, const cuuint64_t*,
                             const cuuint32_t*, const cuuint32_t*, CUtensorMapInterleave, CUtensorMapSwizzle,
                             CUtensorMapL2promotion, CUtensorMapFloatOOBfill);

void make_map(EncodeFn enc, CUtensorMap* tm, const void* base, int rank, const cuuint64_t* dims, const cuuint64_t* strides,
              const cuuint32_t* box, CUtensorMapSwizzle swz) {
  cuuint32_t es[4] = {1, 1, 1, 1};
  enc(tm, CU_TENSOR_MAP_DATA_TYPE_BFLOAT16, rank, const_cast<void*>(base), dims, strides, box, es,
      CU_TENSOR_MAP_INTERLEAVE_NONE, swz, CU_TENSOR_MAP_L2_PROMOTION_L2_256B, CU_TENSOR_MAP_FLOAT_OOB_FILL_NONE);
}

}

extern "C" void kernel_launch(void* const* d_in, const int* in_sizes, int n_in, void* d_out, int out_size) {
  static EncodeFn enc = nullptr;
  static bool coresident = true;
  if (!enc) {
    void* fn = nullptr;
    cudaDriverEntryPointQueryResult qr;
    cudaGetDriverEntryPoint("cuTensorMapEncodeTiled", &fn, cudaEnableDefault, &qr);
    enc = (EncodeFn)fn;
    cudaFuncSetAttribute(fused_kernel<0>, cudaFuncAttributeMaxDynamicSharedMemorySize, SMEM_BYTES);
    cudaFuncSetAttribute(fused_kernel<1>, cudaFuncAttributeMaxDynamicSharedMemorySize, SMEM_BYTES);
    cudaFuncSetAttribute(fused_kernel<2>, cudaFuncAttributeMaxDynamicSharedMemorySize, SMEM_BYTES);
    cudaLaunchConfig_t cfg = {};
    cfg.gridDim = dim3(NCTA);
    cfg.blockDim = dim3(NTHREADS);
    cfg.dynamicSmemBytes = SMEM_BYTES;
    cudaLaunchAttribute at;
    at.id = cudaLaunchAttributeClusterDimension;
    at.val.clusterDim.x = 2;
    at.val.clusterDim.y = 1;
    at.val.clusterDim.z = 1;
    cfg.attrs = &at;
    cfg.numAttrs = 1;
    int nclusters = 0;
    if (cudaOccupancyMaxActiveClusters(&nclusters, fused_kernel<0>, &cfg) == cudaSuccess) coresident = nclusters >= NCTA / 2;
    (void)cudaGetLastError();
  }
  CUtensorMap tmX, tmW, tmWo, tmQ, tmXh, tmWh;
  {
    cuuint64_t dims[3] = {1024, 2, 1024};
    cuuint64_t str[2] = {2048, 4096};
    cuuint32_t box[3] = {64, 1, 128};
    make_map(enc, &tmX, d_in[6], 3, dims, str, box, CU_TENSOR_MAP_SWIZZLE_128B);
  }
  {
    cuuint64_t dims[3] = {1024, 1024, 3};
    cuuint64_t str[2] = {6144, 2048};
    cuuint32_t box[3] = {64, 32, 3};
    make_map(enc, &tmW, d_in[7], 3, dims, str, box, CU_TENSOR_MAP_SWIZZLE_128B);
  }
  {
    cuuint64_t dims[3] = {64, 1024, 16};
    cuuint64_t str[2] = {2048, 128};
    cuuint32_t box[3] = {64, 64, 2};
    make_map(enc, &tmWo, d_in[8], 3, dims, str, box, CU_TENSOR_MAP_SWIZZLE_128B);
  }
  {
    cuuint64_t dims[2] = {1024, 2048};
    cuuint64_t str[1] = {2048};
    cuuint32_t box[2] = {16, 128};
    make_map(enc, &tmQ, d_in[0], 2, dims, str, box, CU_TENSOR_MAP_SWIZZLE_NONE);
  }
  {
    cuuint64_t dims[4] = {1024, 256, 2, 4};
    cuuint64_t str[3] = {4096, 2048, 256 * 4096};
    cuuint32_t box[4] = {64, 8, 2, 4};
    make_map(enc, &tmXh, d_in[6], 4, dims, str, box, CU_TENSOR_MAP_SWIZZLE_128B);
  }
  {
    cuuint64_t dims[3] = {64, 1024, 48};
    cuuint64_t str[2] = {6144, 128};
    cuuint32_t box[3] = {64, 64, 4};
    make_map(enc, &tmWh, d_in[7], 3, dims, str, box, CU_TENSOR_MAP_SWIZZLE_128B);
  }
  Params p;
  p.q = (const __nv_bfloat16*)d_in[0];
  p.k = (const __nv_bfloat16*)d_in[1];
  p.v = (const __nv_bfloat16*)d_in[2];
  p.shift_k = (const __nv_bfloat16*)d_in[3];
  p.ssm_k = (const __nv_bfloat16*)d_in[4];
  p.ssm_D = (const __nv_bfloat16*)d_in[5];
  p.x = (const __nv_bfloat16*)d_in[6];
  p.w = (const __nv_bfloat16*)d_in[7];
  p.wo = (const __nv_bfloat16*)d_in[8];
  p.out = (__nv_bfloat16*)d_out;
  if (coresident) {
    fused_kernel<0><<<NCTA, NTHREADS, SMEM_BYTES>>>(p, tmX, tmW, tmWo, tmQ, tmXh, tmWh);
  } else {
    fused_kernel<0><<<4, NTHREADS, SMEM_BYTES>>>(p, tmX, tmW, tmWo, tmQ, tmXh, tmWh);
    fused_kernel<1><<<NCTA, NTHREADS, SMEM_BYTES>>>(p, tmX, tmW, tmWo, tmQ, tmXh, tmWh);
    fused_kernel<2><<<NCTA, NTHREADS, SMEM_BYTES>>>(p, tmX, tmW, tmWo, tmQ, tmXh, tmWh);
  }
}
```

```cpp
#include <cuda_runtime.h>
#include <cuda.h>
#include <cuda_bf16.h>
#include <stdint.h>

namespace {

constexpr int SEQ = 2048;
constexpr int DM = 1024;
constexpr int NCTA = 132;
constexpr int NTHREADS = 384;

constexpr int STG1A = 32768;
constexpr int NS1A = 3;
constexpr int STG1B = 12288;
constexpr int NS1B = 5;
constexpr int OFF_1B = NS1A * STG1A;
constexpr int STG2 = 32768;
constexpr int NS2 = 5;
constexpr int STGH = 73728;
constexpr int OFF_VP = 0;
constexpr int OFF_KH = 1 * STG2;
constexpr int OFF_OP = 2 * STG2;
constexpr int OFF_Q = 3 * STG2;
constexpr int T_A4 = 0, T_TW = 16384, T_B2 = 24576, T_A1 = 28672, T_END = 32768;
constexpr int OFF_U = 163840;
constexpr int OFF_H = OFF_U + 32768;
constexpr int OFF_T = OFF_U - T_END;
constexpr int OFF_LAND = 4 * STG2;
constexpr int OFF_BAR = OFF_H + 32768;
constexpr int OFF_SC = OFF_BAR + 512;
constexpr int OFF_L0 = OFF_BAR + 1024;
constexpr int SMEM_BYTES = OFF_L0 + 2048;
static_assert(OFF_T + T_A1 == OFF_1B + NS1B * STG1B && OFF_T + T_TW == OFF_1B + 4 * STG1B && OFF_LAND == OFF_T + T_A4, "layout");
static_assert(3 * STGH <= OFF_BAR && SMEM_BYTES <= 232448, "smem");

constexpr int BAR_FULLA = 0;
constexpr int BAR_EMPTYA = 3;
constexpr int BAR_FULLB = 6;
constexpr int BAR_EMPTYB = 11;
constexpr int BAR_FULL2 = 16;
constexpr int BAR_EMPTY2 = 21;
constexpr int BAR_T = 26;
constexpr int BAR_UH = 27;
constexpr int BAR_LFREE = 28;
constexpr int BAR_LAND = 29;
constexpr int BAR_U = 30;
constexpr int BAR_Q = 31;
constexpr int BAR_STG = 32;
constexpr int BAR_DEAD = 33;
constexpr int BAR_X = 35;
constexpr int BAR_REL = 36;

constexpr int NB_G1DONE = 1;
constexpr int NB_OREADY = 2;
constexpr int NB_WG = 4;
constexpr int NB_HELP3 = 6;
constexpr int NB_FIRST = 7;

#define PACE 480u
#define SCHED 1
#define REG_MATH 224
#define REG_HELP 56
constexpr int SPIN_LIMIT = 1 << 20;

__device__ __align__(1024) __nv_bfloat16 g_o[SEQ * DM];
__device__ uint32_t g_flag_o[256];
__device__ uint32_t g_flag_h[4];
__device__ uint4 g_halo[128 * 128];
__device__ __align__(128) const uint32_t g_tab[T_END / 4] = {
0x3c003c00,0x3bf13bff,0,0xafd6a648,0x3c003c00,0x3b993bce,0,0xb505b303,0x3c003c00,0x3af63b50,0,0xb7e3b67c,
0x3c003c00,0x3a0f3a8a,0,0xb93ab89b,0x3bc33bfe,0x3b773bfa,0xb3c6aa48,0xb5c2acb5,0x3a6d3b3b,0x389b3a4f,0xb8c4b6d7,0xba8ab8ec,
0x381d395f,0x26483505,0xbaddb9ed,0xbbffbb99,0x30b23564,0xb848b444,0xbbeabb88,0xbac2bbb6,0x3b0e3bf6,0x3a8a3bf1,0xb78bae46,0xb89bafd6,
0x34a53913,0xa6483732,0xbba8ba2f,0xbbffbb25,0xb78bae46,0xbac2b7e3,0xbb0ebbf6,0xb848baf6,0xbba8ba2f,0xbb50bbfa,0xb4a5b913,0x367cacb5,
0x39ed3bea,0x393a3be2,0xb95fb0b2,0xba0fb179,0xb56433c6,0xb8ec2648,0xbb88bbc3,0xba4fbbff,0xbbfeba6d,0xbb25bbce,0xaa48b8c4,0x3732b303,
0xb6d7badd,0x3444b67c,0x3b3b381d,0x3bb63b50,0x38723bd9,0x37323bce,0xbaa7b23e,0xbb25b303,0xbaa7b23e,0xbbb6b67c,0xb872bbd9,0xb444bb50,
0xb872bbd9,0xacb5ba8a,0x3aa7323e,0x3bfa389b,0x3aa7323e,0x3bf139cb,0x38723bd9,0xafd63984,0x35643bc3,0x33033bb6,0xbb88b3c6,0xbbceb444,
0xbbfeb8c4,0xbb77ba0f,0x2a48ba6d,0x35c2b93a,0x36d7b81d,0x3a8aafd6,0x3b3b3add,0x389b3bf1,0x395f3bea,0x26483b25,0xb9ed30b2,0xbbffb732,
0x2e463ba8,0xa6483b99,0xbbf6b4a5,0xbbffb505,0xba2fbb0e,0xb848bbb6,0x3913b78b,0x3ac2b444,0x3bf634a5,0x3b50393a,0x2e463ba8,0xb67c3a0f,
0xb913378b,0xbbe2afd6,0xba2fbb0e,0xb179bbf1,0xb0b23b88,0xb4443b77,0xbbeab564,0xbbb6b5c2,0xb3c6bbfe,0x2cb5bbe2,0x3bc3aa48,0x3bfa3179,
0x38c43b3b,0x2fd63bff,0xba6d36d7,0xbbf12648,0xbaddb95f,0xb505bbce,0x381db9ed,0x3b99b303,0xb61f3b64,0xb7e33b50,0xbb64b61f,0xbaf6b67c,
0x361fbb64,0x393aba8a,0x3b64361f,0x3a0f389b,0xb61f3b64,0xba4f3984,0xbb64b61f,0xb8ecb9cb,0x361fbb64,0x3b25b848,0x3b64361f,0x37323ac2,
0xb8c43b3b,0xb9843b25,0xba6db6d7,0xb9cbb732,0x3addb95f,0x3bceb7e3,0x381d39ed,0x33033af6,0xbbea3564,0xbb77acb5,0xb0b2bb88,0x35c2bbfa,
0x3bc32a48,0x389b38ec,0xb3c63bfe,0xba8a3a4f,0xba2f3b0e,0xbac23af6,0xb913b78b,0xb848b7e3,0x3bf6b4a5,0x3b50acb5,0xae463ba8,0xb67c3bfa,
0xb913b78b,0xb179ba4f,0x3a2fbb0e,0x3be2b8ec,0xae463ba8,0xb9cb3b99,0xbbf634a5,0xb984b505,0xbb3b3add,0xbb993ac2,0xb6d7b81d,0xb505b848,
0x39ed30b2,0x37e335c2,0xb95f3bea,0xbaf63b77,0x3564bbc3,0x3a0fbbe2,0x3b88b3c6,0x393a3179,0xbbfe38c4,0xba4f2648,0xaa48ba6d,0x38ecbbff,
0xbbd93aa7,0xbbfa3a8a,0xb23eb872,0xacb5b89b,0x323e3872,0xafd639cb,0xbbd93aa7,0xbbf13984,0x3bd9baa7,0x3b99b848,0x323e3872,0xb5053ac2,
0xb23eb872,0x37e3bb77,0x3bd9baa7,0x3af6b5c2,0xbbfe3a6d,0xbbe23a4f,0x2a48b8c4,0x3179b8ec,0xb6d73add,0xb9843b99,0xbb3b381d,0xb9cb3505,
0x395fb0b2,0x33033444,0xb9ed3bea,0xbbce3bb6,0x3b88bbc3,0x3b77b93a,0x356433c6,0xb5c23a0f,0xbba83a2f,0xbb503a0f,0x34a5b913,0x367cb93a,
0xbb0e3bf6,0xbbe23bf1,0xb78b2e46,0xb179afd6,0xb4a53913,0xb9cb3b25,0xbba83a2f,0xb9843732,0x378bae46,0xb30337e3,0xbb0e3bf6,0xbbce3af6,
0xbadd39ed,0xba4f39cb,0x381db95f,0x38ecb984,0xbbea3b88,0xbb253ac2,0x30b2b564,0x3732b848,0xbbc33bfe,0xbbb63b77,0xb3c62a48,0x3444b5c2,
0xba6d3b3b,0xbbfa3be2,0xb8c436d7,0x2cb5b179,0xb9a839a8,0xb8ec3984,0x39a8b9a8,0x3a4fb9cb,0xb9a839a8,0xb7323848,0x39a8b9a8,0x3b25bac2,
0xb9a839a8,0xb44435c2,0x39a8b9a8,0x3bb6bb77,0xb9a839a8,0xacb53179,0x39a8b9a8,0x3bfabbe2,0xb81d395f,0xb67c393a,0x3addb9ed,0x3b50ba0f,
0xb0b23564,0x31792fd6,0x3beabb88,0x3be2bbf1,0x33c6aa48,0x3984b732,0x3bc3bbfe,0x39cbbb25,0x38c4b6d7,0x3bcebaf6,0x3a6dbb3b,0x3303b7e3,
0xb4a53913,0xb17938ec,0x3ba8ba2f,0x3be2ba4f,0x378bae46,0x39cbb505,0x3b0ebbf6,0x3984bb99,0x3ba8ba2f,0x3bcebbb6,0x34a5b913,0xb303b444,
0x3b0ebbf6,0x35c2ba0f,0xb78b2e46,0xbb77393a,0xaa4838c4,0x2cb5389b,0x3bfeba6d,0x3bfaba8a,0x3b3bb81d,0x3bf1b984,0x36d7badd,0x2fd6b9cb,
0x39edbbea,0x3505bac2,0xb95f30b2,0xbb993848,0xb564b3c6,0xbaf635c2,0xbb883bc3,0xb7e33b77,0x323e3872,0x35053848,0x3bd9baa7,0x3b99bac2,
0x3bd9baa7,0x3af6bb77,0xb23eb872,0xb7e3b5c2,0xb23eb872,0xb93ab179,0xbbd93aa7,0xba0f3be2,0xbbd93aa7,0xb8ec3bff,0x323e3872,0x3a4fa648,
0x36d7381d,0x384837e3,0x3b3bbadd,0x3ac2baf6,0x395fbbea,0x367cbbfa,0xb9edb0b2,0xbb502cb5,0xbb8833c6,0xbbe238ec,0xb5643bc3,0x31793a4f,
0x2a483a6d,0x39843505,0x3bfeb8c4,0x39cbbb99,0x3913378b,0x39cb3732,0x3a2fbb0e,0x3984bb25,0x2e46bba8,0xb303baf6,0xbbf634a5,0xbbce37e3,
0xba2f3b0e,0xb5c23bfa,0x3913378b,0x3b772cb5,0x3bf6b4a5,0x3a8aba4f,0x2e46bba8,0xb89bb8ec,0x3a6d36d7,0x3af6367c,0x38c4bb3b,0x37e3bb50,
0xb81db9ed,0xba0fb89b,0xbadd395f,0xb93a3a8a,0x30b23b88,0x38ec39cb,0x3beab564,0x3a4fb984,0x33c6bbfe,0xb732bac2,0xbbc3aa48,0xbb253848,
0x3b64361f,0x3bb635c2,0x361fbb64,0x3444bb77,0xbb64b61f,0xbbfab179,0xb61f3b64,0xacb53be2,0x3b64361f,0x3bf1a648,0x361fbb64,0xafd6bbff,
0xbb64b61f,0xbb993303,0xb61f3b64,0x35053bce,0x3bea3564,0x3bff3505,0x30b2bb88,0x2648bb99,0xbbc32a48,0xbac23444,0x33c63bfe,0x38483bb6,
0x3a6db6d7,0x367cba0f,0xb8c4bb3b,0xbb50b93a,0xb81d39ed,0x31793bf1,0x3add395f,0x3be22fd6,0x3bf634a5,0x3bce3444,0xae46bba8,0xb303bbb6,
0xb913378b,0xb5c2393a,0x3a2f3b0e,0x3b773a0f,0xae46bba8,0xb89bbbf1,0xbbf6b4a5,0xba8a2fd6,0x3a2f3b0e,0x3bff3732,0x3913b78b,0xa648bb25,
0x3b8833c6,0x3b253303,0xb564bbc3,0xb732bbce,0xaa483a6d,0x34443b50,0x3bfe38c4,0x3bb6367c,0xbb3bbadd,0xbbfab89b,0xb6d7381d,0x2cb53a8a,
0x39edb0b2,0x2fd6b984,0xb95fbbea,0xbbf1b9cb,0x3aa7323e,0x3a0f3179,0xb872bbd9,0xb93abbe2,0x38723bd9,0x3a4f3bff,0x3aa7323e,0x38eca648,
0xbaa7b23e,0xb7323303,0x38723bd9,0x3b253bce,0xb872bbd9,0xbbb6bb50,0xbaa7b23e,0xb444367c,0x395f30b2,0x389b2fd6,0xb9edbbea,0xba8abbf1,
0x3b883bc3,0x3bff3b25,0x3564b3c6,0x2648b732,0x2a4838c4,0x38483af6,0x3bfe3a6d,0x3ac237e3,0xbb3bb81d,0xb67c2cb5,0x36d73add,0x3b503bfa,
0x378b2e46,0x35c22cb5,0xbb0ebbf6,0xbb77bbfa,0x3ba83a2f,0x3a8a38ec,0xb4a5b913,0xb89bba4f,0x3b0e3bf6,0x3bff3b99,0x378b2e46,0xa648b505,
0x34a53913,0x3ac23bb6,0x3ba83a2f,0x38483444,0x33c62a48,0x2fd62648,0xbbc3bbfe,0xbbf1bbff,0x38c436d7,0x35053303,0xba6dbb3b,0xbb99bbce,
0x3add39ed,0x37e3367c,0xb81db95f,0xbaf6bb50,0x3bea3b88,0x393a389b,0xb0b2b564,0xba0fba8a,0x3c003c00,0xbbf1bbff,0,0x2fd62648,
0x3c003c00,0xbb99bbce,0,0x35053303,0x3c003c00,0xbaf6bb50,0,0x37e3367c,0x3c003c00,0xba0fba8a,0,0x393a389b,
0x3bc33bfe,0xbb77bbfa,0xb3c6aa48,0x35c22cb5,0x3a6d3b3b,0xb89bba4f,0xb8c4b6d7,0x3a8a38ec,0x381d395f,0xa648b505,0xbaddb9ed,0x3bff3b99,
0x30b23564,0x38483444,0xbbeabb88,0x3ac23bb6,0x3b0e3bf6,0xba8abbf1,0xb78bae46,0x389b2fd6,0x34a53913,0x2648b732,0xbba8ba2f,0x3bff3b25,
0xb78bae46,0x3ac237e3,0xbb0ebbf6,0x38483af6,0xbba8ba2f,0x3b503bfa,0xb4a5b913,0xb67c2cb5,0x39ed3bea,0xb93abbe2,0xb95fb0b2,0x3a0f3179,
0xb56433c6,0x38eca648,0xbb88bbc3,0x3a4f3bff,0xbbfeba6d,0x3b253bce,0xaa48b8c4,0xb7323303,0xb6d7badd,0xb444367c,0x3b3b381d,0xbbb6bb50,
0x38723bd9,0xb732bbce,0xbaa7b23e,0x3b253303,0xbaa7b23e,0x3bb6367c,0xb872bbd9,0x34443b50,0xb872bbd9,0x2cb53a8a,0x3aa7323e,0xbbfab89b,
0x3aa7323e,0xbbf1b9cb,0x38723bd9,0x2fd6b984,0x35643bc3,0xb303bbb6,0xbb88b3c6,0x3bce3444,0xbbfeb8c4,0x3b773a0f,0x2a48ba6d,0xb5c2393a,
0x36d7b81d,0xba8a2fd6,0x3b3b3add,0xb89bbbf1,0x395f3bea,0xa648bb25,0xb9ed30b2,0x3bff3732,0x2e463ba8,0x2648bb99,0xbbf6b4a5,0x3bff3505,
0xba2fbb0e,0x38483bb6,0x3913b78b,0xbac23444,0x3bf634a5,0xbb50b93a,0x2e463ba8,0x367cba0f,0xb913378b,0x3be22fd6,0xba2fbb0e,0x31793bf1,
0xb0b23b88,0x3444bb77,0xbbeab564,0x3bb635c2,0xb3c6bbfe,0xacb53be2,0x3bc3aa48,0xbbfab179,0x38c43b3b,0xafd6bbff,0xba6d36d7,0x3bf1a648,
0xbaddb95f,0x35053bce,0x381db9ed,0xbb993303,0xb61f3b64,0x37e3bb50,0xbb64b61f,0x3af6367c,0x361fbb64,0xb93a3a8a,0x3b64361f,0xba0fb89b,
0xb61f3b64,0x3a4fb984,0xbb64b61f,0x38ec39cb,0x361fbb64,0xbb253848,0x3b64361f,0xb732bac2,0xb8c43b3b,0x3984bb25,0xba6db6d7,0x39cb3732,
0x3addb95f,0xbbce37e3,0x381d39ed,0xb303baf6,0xbbea3564,0x3b772cb5,0xb0b2bb88,0xb5c23bfa,0x3bc32a48,0xb89bb8ec,0xb3c63bfe,0x3a8aba4f,
0xba2f3b0e,0x3ac2baf6,0xb913b78b,0x384837e3,0x3bf6b4a5,0xbb502cb5,0xae463ba8,0x367cbbfa,0xb913b78b,0x31793a4f,0x3a2fbb0e,0xbbe238ec,
0xae463ba8,0x39cbbb99,0xbbf634a5,0x39843505,0xbb3b3add,0x3b99bac2,0xb6d7b81d,0x35053848,0x39ed30b2,0xb7e3b5c2,0xb95f3bea,0x3af6bb77,
0x3564bbc3,0xba0f3be2,0x3b88b3c6,0xb93ab179,0xbbfe38c4,0x3a4fa648,0xaa48ba6d,0xb8ec3bff,0xbbd93aa7,0x3bfaba8a,0xb23eb872,0x2cb5389b,
0x323e3872,0x2fd6b9cb,0xbbd93aa7,0x3bf1b984,0x3bd9baa7,0xbb993848,0x323e3872,0x3505bac2,0xb23eb872,0xb7e33b77,0x3bd9baa7,0xbaf635c2,
0xbbfe3a6d,0x3be2ba4f,0x2a48b8c4,0xb17938ec,0xb6d73add,0x3984bb99,0xbb3b381d,0x39cbb505,0x395fb0b2,0xb303b444,0xb9ed3bea,0x3bcebbb6,
0x3b88bbc3,0xbb77393a,0x356433c6,0x35c2ba0f,0xbba83a2f,0x3b50ba0f,0x34a5b913,0xb67c393a,0xbb0e3bf6,0x3be2bbf1,0xb78b2e46,0x31792fd6,
0xb4a53913,0x39cbbb25,0xbba83a2f,0x3984b732,0x378bae46,0x3303b7e3,0xbb0e3bf6,0x3bcebaf6,0xbadd39ed,0x3a4fb9cb,0x381db95f,0xb8ec3984,
0xbbea3b88,0x3b25bac2,0x30b2b564,0xb7323848,0xbbc33bfe,0x3bb6bb77,0xb3c62a48,0xb44435c2,0xba6d3b3b,0x3bfabbe2,0xb8c436d7,0xacb53179,
0xb9a839a8,0x38ecb984,0x39a8b9a8,0xba4f39cb,0xb9a839a8,0x3732b848,0x39a8b9a8,0xbb253ac2,0xb9a839a8,0x3444b5c2,0x39a8b9a8,0xbbb63b77,
0xb9a839a8,0x2cb5b179,0x39a8b9a8,0xbbfa3be2,0xb81d395f,0x367cb93a,0x3addb9ed,0xbb503a0f,0xb0b23564,0xb179afd6,0x3beabb88,0xbbe23bf1,
0x33c6aa48,0xb9843732,0x3bc3bbfe,0xb9cb3b25,0x38c4b6d7,0xbbce3af6,0x3a6dbb3b,0xb30337e3,0xb4a53913,0x3179b8ec,0x3ba8ba2f,0xbbe23a4f,
0x378bae46,0xb9cb3505,0x3b0ebbf6,0xb9843b99,0x3ba8ba2f,0xbbce3bb6,0x34a5b913,0x33033444,0x3b0ebbf6,0xb5c23a0f,0xb78b2e46,0x3b77b93a,
0xaa4838c4,0xacb5b89b,0x3bfeba6d,0xbbfa3a8a,0x3b3bb81d,0xbbf13984,0x36d7badd,0xafd639cb,0x39edbbea,0xb5053ac2,0xb95f30b2,0x3b99b848,
0xb564b3c6,0x3af6b5c2,0xbb883bc3,0x37e3bb77,0x323e3872,0xb505b848,0x3bd9baa7,0xbb993ac2,0x3bd9baa7,0xbaf63b77,0xb23eb872,0x37e335c2,
0xb23eb872,0x393a3179,0xbbd93aa7,0x3a0fbbe2,0xbbd93aa7,0x38ecbbff,0x323e3872,0xba4f2648,0x36d7381d,0xb848b7e3,0x3b3bbadd,0xbac23af6,
0x395fbbea,0xb67c3bfa,0xb9edb0b2,0x3b50acb5,0xbb8833c6,0x3be2b8ec,0xb5643bc3,0xb179ba4f,0x2a483a6d,0xb984b505,0x3bfeb8c4,0xb9cb3b99,
0x3913378b,0xb9cbb732,0x3a2fbb0e,0xb9843b25,0x2e46bba8,0x33033af6,0xbbf634a5,0x3bceb7e3,0xba2f3b0e,0x35c2bbfa,0x3913378b,0xbb77acb5,
0x3bf6b4a5,0xba8a3a4f,0x2e46bba8,0x389b38ec,0x3a6d36d7,0xbaf6b67c,0x38c4bb3b,0xb7e33b50,0xb81db9ed,0x3a0f389b,0xbadd395f,0x393aba8a,
0x30b23b88,0xb8ecb9cb,0x3beab564,0xba4f3984,0x33c6bbfe,0x37323ac2,0xbbc3aa48,0x3b25b848,0x3b64361f,0xbbb6b5c2,0x361fbb64,0xb4443b77,
0xbb64b61f,0x3bfa3179,0xb61f3b64,0x2cb5bbe2,0x3b64361f,0xbbf12648,0x361fbb64,0x2fd63bff,0xbb64b61f,0x3b99b303,0xb61f3b64,0xb505bbce,
0x3bea3564,0xbbffb505,0x30b2bb88,0xa6483b99,0xbbc32a48,0x3ac2b444,0x33c63bfe,0xb848bbb6,0x3a6db6d7,0xb67c3a0f,0xb8c4bb3b,0x3b50393a,
0xb81d39ed,0xb179bbf1,0x3add395f,0xbbe2afd6,0x3bf634a5,0xbbceb444,0xae46bba8,0x33033bb6,0xb913378b,0x35c2b93a,0x3a2f3b0e,0xbb77ba0f,
0xae46bba8,0x389b3bf1,0xbbf6b4a5,0x3a8aafd6,0x3a2f3b0e,0xbbffb732,0x3913b78b,0x26483b25,0x3b8833c6,0xbb25b303,0xb564bbc3,0x37323bce,
0xaa483a6d,0xb444bb50,0x3bfe38c4,0xbbb6b67c,0xbb3bbadd,0x3bfa389b,0xb6d7381d,0xacb5ba8a,0x39edb0b2,0xafd63984,0xb95fbbea,0x3bf139cb,
0x3aa7323e,0xba0fb179,0xb872bbd9,0x393a3be2,0x38723bd9,0xba4fbbff,0x3aa7323e,0xb8ec2648,0xbaa7b23e,0x3732b303,0x38723bd9,0xbb25bbce,
0xb872bbd9,0x3bb63b50,0xbaa7b23e,0x3444b67c,0x395f30b2,0xb89bafd6,0xb9edbbea,0x3a8a3bf1,0x3b883bc3,0xbbffbb25,0x3564b3c6,0xa6483732,
0x2a4838c4,0xb848baf6,0x3bfe3a6d,0xbac2b7e3,0xbb3bb81d,0x367cacb5,0x36d73add,0xbb50bbfa,0x378b2e46,0xb5c2acb5,0xbb0ebbf6,0x3b773bfa,
0x3ba83a2f,0xba8ab8ec,0xb4a5b913,0x389b3a4f,0x3b0e3bf6,0xbbffbb99,0x378b2e46,0x26483505,0x34a53913,0xbac2bbb6,0x3ba83a2f,0xb848b444,
0x33c62a48,0xafd6a648,0xbbc3bbfe,0x3bf13bff,0x38c436d7,0xb505b303,0xba6dbb3b,0x3b993bce,0x3add39ed,0xb7e3b67c,0xb81db95f,0x3af63b50,
0x3bea3b88,0xb93ab89b,0xb0b2b564,0x3a0f3a8a,0x3c003c00,0x38ec3984,0,0xba4fb9cb,0x3c003c00,0x37323848,0,0xbb25bac2,
0x3c003c00,0x344435c2,0,0xbbb6bb77,0x3c003c00,0x2cb53179,0,0xbbfabbe2,0xb3c6aa48,0xbb50ba0f,0xbbc3bbfe,0xb67cb93a,
0xb8c4b6d7,0xbbe2bbf1,0xba6dbb3b,0x3179afd6,0xbaddb9ed,0xb9cbbb25,0xb81db95f,0x39843732,0xbbeabb88,0xb303b7e3,0xb0b2b564,0x3bce3af6,
0xbb0ebbf6,0xb179b8ec,0x378b2e46,0x3be23a4f,0xb4a5b913,0x39cb3505,0x3ba83a2f,0x39843b99,0x378b2e46,0x3bce3bb6,0x3b0e3bf6,0xb3033444,
0x3ba83a2f,0x35c23a0f,0x34a53913,0xbb77b93a,0x395f30b2,0x3bfa3a8a,0x39ed3bea,0xacb5389b,0x3b883bc3,0x2fd639cb,0xb56433c6,0xbbf1b984,
0x2a4838c4,0xbb99b848,0xbbfeba6d,0xb505bac2,0xbb3bb81d,0xb7e3bb77,0xb6d7badd,0x3af635c2,0x38723bd9,0xb5053848,0xbaa7b23e,0xbb99bac2,
0xbaa7b23e,0xbaf6bb77,0xb872bbd9,0x37e3b5c2,0xb872bbd9,0x393ab179,0x3aa7323e,0x3a0f3be2,0x3aa7323e,0x38ec3bff,0x38723bd9,0xba4fa648,
0xbb88b3c6,0xbac2baf6,0xb564bbc3,0x3848b7e3,0x2a48ba6d,0x3b502cb5,0x3bfe38c4,0x367c3bfa,0x3b3b3add,0xb1793a4f,0xb6d7381d,0xbbe2b8ec,
0xb9ed30b2,0xb9cbbb99,0xb95fbbea,0x3984b505,0xae46bba8,0x39cbb732,0x3bf634a5,0x39843b25,0x3a2f3b0e,0xb3033af6,0xb913378b,0xbbceb7e3,
0xbbf6b4a5,0xb5c2bbfa,0xae46bba8,0x3b77acb5,0x3913b78b,0x3a8a3a4f,0x3a2f3b0e,0xb89b38ec,0x3bea3564,0x37e33b50,0xb0b23b88,0xbaf6367c,
0xbbc32a48,0xb93aba8a,0xb3c6bbfe,0x3a0fb89b,0x3a6db6d7,0x3a4f3984,0x38c43b3b,0xb8ec39cb,0xb81d39ed,0xbb25b848,0xbaddb95f,0x3732bac2,
0xb61f3b64,0xbbb635c2,0xbb64b61f,0xb444bb77,0x361fbb64,0x3bfab179,0x3b64361f,0x2cb53be2,0xb61f3b64,0xbbf1a648,0xbb64b61f,0x2fd6bbff,
0x361fbb64,0x3b993303,0x3b64361f,0xb5053bce,0xba6db6d7,0xa648bb99,0x38c4bb3b,0x3bffb505,0x381d39ed,0xb8483bb6,0xbadd395f,0xbac2b444,
0xb0b2bb88,0x3b50b93a,0x3beab564,0x367c3a0f,0xb3c63bfe,0xbbe22fd6,0xbbc3aa48,0x3179bbf1,0x3a2fbb0e,0x3bceb444,0x3913378b,0xb3033bb6,
0xbbf634a5,0xb5c2b93a,0x2e46bba8,0x3b77ba0f,0x3913378b,0xb89b3bf1,0xba2f3b0e,0xba8aafd6,0x2e46bba8,0x3bffb732,0x3bf6b4a5,0xa6483b25,
0x36d7381d,0xb7323bce,0xbb3b3add,0xbb253303,0x395fbbea,0x3bb6b67c,0x39ed30b2,0xb4443b50,0xbb8833c6,0x2cb5ba8a,0x3564bbc3,0x3bfab89b,
0x2a483a6d,0xbbf139cb,0xbbfe38c4,0xafd6b984,0xbbd93aa7,0xba0f3179,0xb23eb872,0x393abbe2,0x323e3872,0xba4f3bff,0xbbd93aa7,0xb8eca648,
0x3bd9baa7,0x37323303,0x323e3872,0xbb253bce,0xb23eb872,0x3bb6bb50,0x3bd9baa7,0x3444367c,0x2a48b8c4,0x3a8abbf1,0x3bfeba6d,0x389bafd6,
0xbb3b381d,0xa648b732,0x36d7badd,0x3bffbb25,0xb9ed3bea,0xbac237e3,0xb95f30b2,0x3848baf6,0x356433c6,0xbb503bfa,0xbb883bc3,0xb67cacb5,
0x3ba8ba2f,0x35c2acb5,0xb4a53913,0xbb773bfa,0x3b0ebbf6,0x3a8ab8ec,0x378bae46,0xb89b3a4f,0x34a5b913,0x3bffbb99,0x3ba8ba2f,0xa6483505,
0xb78b2e46,0x3ac2bbb6,0x3b0ebbf6,0x3848b444,0xb81d395f,0xbbf13bff,0xbadd39ed,0xafd62648,0xb0b23564,0xbb993bce,0xbbea3b88,0xb5053303,
0x33c6aa48,0xbaf63b50,0xbbc33bfe,0xb7e3367c,0x38c4b6d7,0xba0f3a8a,0xba6d3b3b,0xb93a389b,0xb9a839a8,0x2fd6a648,0x39a8b9a8,0x3bf1bbff,
0xb9a839a8,0x3505b303,0x39a8b9a8,0x3b99bbce,0xb9a839a8,0x37e3b67c,0x39a8b9a8,0x3af6bb50,0xb9a839a8,0x393ab89b,0x39a8b9a8,0x3a0fba8a,
0x3addb9ed,0x3b77bbfa,0x381db95f,0xb5c22cb5,0x3beabb88,0x389bba4f,0x30b2b564,0xba8a38ec,0x3bc3bbfe,0x2648b505,0xb3c62a48,0xbbff3b99,
0x3a6dbb3b,0xb8483444,0xb8c436d7,0xbac23bb6,0x34a5b913,0xb89b2fd6,0xbba83a2f,0xba8a3bf1,0xb78b2e46,0xbbff3b25,0xbb0e3bf6,0x26483732,
0xbba83a2f,0xb8483af6,0xb4a53913,0x3ac2b7e3,0xbb0e3bf6,0x367c2cb5,0x378bae46,0x3b50bbfa,0xbbfe3a6d,0xb93a3be2,0xaa4838c4,0x3a0fb179,
0xb6d73add,0x38ec2648,0x3b3bb81d,0x3a4fbbff,0x395fb0b2,0x3b25bbce,0x39edbbea,0xb732b303,0x3b88bbc3,0xb444b67c,0xb564b3c6,0xbbb63b50,
0x323e3872,0x3b25b303,0x3bd9baa7,0x3732bbce,0x3bd9baa7,0x3444bb50,0xb23eb872,0xbbb6367c,0xb23eb872,0xbbfa389b,0xbbd93aa7,0xacb53a8a,
0xbbd93aa7,0x2fd63984,0x323e3872,0x3bf1b9cb,0x3b3bbadd,0x3303bbb6,0xb6d7b81d,0xbbce3444,0xb9edb0b2,0xbb773a0f,0xb95f3bea,0x35c2393a,
0xb5643bc3,0x3a8a2fd6,0x3b88b3c6,0x389bbbf1,0x3bfeb8c4,0x2648bb25,0xaa48ba6d,0xbbff3732,0xb913b78b,0xbbff3505,0xba2f3b0e,0x26483b99,
0xae463ba8,0x3ac23444,0x3bf6b4a5,0x3848bbb6,0x3a2fbb0e,0xb67cba0f,0xb913b78b,0xbb50393a,0xbbf634a5,0xb1793bf1,0xae463ba8,0x3be2afd6,
0xb8c43b3b,0x34443b77,0x3a6d36d7,0x3bb6b5c2,0x3addb95f,0xacb5bbe2,0xb81db9ed,0xbbfa3179,0xbbea3564,0xafd63bff,0x30b23b88,0x3bf12648,
0x3bc32a48,0x3505bbce,0x33c6bbfe,0xbb99b303,0x3b64361f,0x3af6b67c,0x361fbb64,0xb7e3bb50,0xbb64b61f,0xba0f389b,0xb61f3b64,0x393a3a8a,
0x3b64361f,0x38ecb9cb,0x361fbb64,0xba4fb984,0xbb64b61f,0xb7323ac2,0xb61f3b64,0x3b253848,0x30b2bb88,0xb984bb25,0xbbeab564,0xb9cb3732,
0x33c63bfe,0x3bce37e3,0x3bc3aa48,0x3303baf6,0xb8c4bb3b,0xbb772cb5,0xba6d36d7,0x35c23bfa,0x3add395f,0x389bb8ec,0x381db9ed,0xba8aba4f,
0xbbf6b4a5,0xb84837e3,0x2e463ba8,0x3ac23af6,0x3913b78b,0xb67cbbfa,0xba2fbb0e,0xbb50acb5,0x2e463ba8,0x3be238ec,0x3bf634a5,0x3179ba4f,
0xba2fbb0e,0xb9843505,0xb913378b,0x39cb3b99,0x35643bc3,0x3b993ac2,0x3b8833c6,0x3505b848,0xbbfeb8c4,0xb7e335c2,0xaa483a6d,0x3af63b77,
0x36d7b81d,0xba0fbbe2,0xbb3bbadd,0xb93a3179,0x395f3bea,0x3a4f2648,0x39edb0b2,0xb8ecbbff,0x3aa7323e,0x2cb5b89b,0xb872bbd9,0xbbfaba8a,
0x38723bd9,0x3bf13984,0x3aa7323e,0xafd6b9cb,0xbaa7b23e,0x35053ac2,0x38723bd9,0x3b993848,0xb872bbd9,0xbaf6b5c2,0xbaa7b23e,0x37e33b77,
0xb9edbbea,0xbbe2ba4f,0xb95fb0b2,0x317938ec,0x3564b3c6,0xb984bb99,0xbb88bbc3,0xb9cbb505,0x3bfe3a6d,0x3303b444,0xaa48b8c4,0xbbcebbb6,
0x36d73add,0x3b77393a,0x3b3b381d,0xb5c2ba0f,0xb78bae46,0x367c393a,0x3b0e3bf6,0x3b503a0f,0xbba8ba2f,0xb1792fd6,0x34a53913,0x3be23bf1,
0xbb0ebbf6,0xb984b732,0xb78bae46,0x39cb3b25,0xb4a5b913,0xbbcebaf6,0xbba8ba2f,0x330337e3,0x3bc33bfe,0x3a4f39cb,0x33c62a48,0xb8ecb984,
0x3a6d3b3b,0x3b253ac2,0x38c436d7,0xb732b848,0x381d395f,0x3bb63b77,0x3add39ed,0xb444b5c2,0x30b23564,0x3bfa3be2,0x3bea3b88,0xacb5b179,
0x3c003c00,0xb8ecb984,0,0x3a4f39cb,0x3c003c00,0xb732b848,0,0x3b253ac2,0x3c003c00,0xb444b5c2,0,0x3bb63b77,
0x3c003c00,0xacb5b179,0,0x3bfa3be2,0xb3c6aa48,0x3b503a0f,0xbbc3bbfe,0x367c393a,0xb8c4b6d7,0x3be23bf1,0xba6dbb3b,0xb1792fd6,
0xbaddb9ed,0x39cb3b25,0xb81db95f,0xb984b732,0xbbeabb88,0x330337e3,0xb0b2b564,0xbbcebaf6,0xbb0ebbf6,0x317938ec,0x378b2e46,0xbbe2ba4f,
0xb4a5b913,0xb9cbb505,0x3ba83a2f,0xb984bb99,0x378b2e46,0xbbcebbb6,0x3b0e3bf6,0x3303b444,0x3ba83a2f,0xb5c2ba0f,0x34a53913,0x3b77393a,
0x395f30b2,0xbbfaba8a,0x39ed3bea,0x2cb5b89b,0x3b883bc3,0xafd6b9cb,0xb56433c6,0x3bf13984,0x2a4838c4,0x3b993848,0xbbfeba6d,0x35053ac2,
0xbb3bb81d,0x37e33b77,0xb6d7badd,0xbaf6b5c2,0x38723bd9,0x3505b848,0xbaa7b23e,0x3b993ac2,0xbaa7b23e,0x3af63b77,0xb872bbd9,0xb7e335c2,
0xb872bbd9,0xb93a3179,0x3aa7323e,0xba0fbbe2,0x3aa7323e,0xb8ecbbff,0x38723bd9,0x3a4f2648,0xbb88b3c6,0x3ac23af6,0xb564bbc3,0xb84837e3,
0x2a48ba6d,0xbb50acb5,0x3bfe38c4,0xb67cbbfa,0x3b3b3add,0x3179ba4f,0xb6d7381d,0x3be238ec,0xb9ed30b2,0x39cb3b99,0xb95fbbea,0xb9843505,
0xae46bba8,0xb9cb3732,0x3bf634a5,0xb984bb25,0x3a2f3b0e,0x3303baf6,0xb913378b,0x3bce37e3,0xbbf6b4a5,0x35c23bfa,0xae46bba8,0xbb772cb5,
0x3913b78b,0xba8aba4f,0x3a2f3b0e,0x389bb8ec,0x3bea3564,0xb7e3bb50,0xb0b23b88,0x3af6b67c,0xbbc32a48,0x393a3a8a,0xb3c6bbfe,0xba0f389b,
0x3a6db6d7,0xba4fb984,0x38c43b3b,0x38ecb9cb,0xb81d39ed,0x3b253848,0xbaddb95f,0xb7323ac2,0xb61f3b64,0x3bb6b5c2,0xbb64b61f,0x34443b77,
0x361fbb64,0xbbfa3179,0x3b64361f,0xacb5bbe2,0xb61f3b64,0x3bf12648,0xbb64b61f,0xafd63bff,0x361fbb64,0xbb99b303,0x3b64361f,0x3505bbce,
0xba6db6d7,0x26483b99,0x38c4bb3b,0xbbff3505,0x381d39ed,0x3848bbb6,0xbadd395f,0x3ac23444,0xb0b2bb88,0xbb50393a,0x3beab564,0xb67cba0f,
0xb3c63bfe,0x3be2afd6,0xbbc3aa48,0xb1793bf1,0x3a2fbb0e,0xbbce3444,0x3913378b,0x3303bbb6,0xbbf634a5,0x35c2393a,0x2e46bba8,0xbb773a0f,
0x3913378b,0x389bbbf1,0xba2f3b0e,0x3a8a2fd6,0x2e46bba8,0xbbff3732,0x3bf6b4a5,0x2648bb25,0x36d7381d,0x3732bbce,0xbb3b3add,0x3b25b303,
0x395fbbea,0xbbb6367c,0x39ed30b2,0x3444bb50,0xbb8833c6,0xacb53a8a,0x3564bbc3,0xbbfa389b,0x2a483a6d,0x3bf1b9cb,0xbbfe38c4,0x2fd63984,
0xbbd93aa7,0x3a0fb179,0xb23eb872,0xb93a3be2,0x323e3872,0x3a4fbbff,0xbbd93aa7,0x38ec2648,0x3bd9baa7,0xb732b303,0x323e3872,0x3b25bbce,
0xb23eb872,0xbbb63b50,0x3bd9baa7,0xb444b67c,0x2a48b8c4,0xba8a3bf1,0x3bfeba6d,0xb89b2fd6,0xbb3b381d,0x26483732,0x36d7badd,0xbbff3b25,
0xb9ed3bea,0x3ac2b7e3,0xb95f30b2,0xb8483af6,0x356433c6,0x3b50bbfa,0xbb883bc3,0x367c2cb5,0x3ba8ba2f,0xb5c22cb5,0xb4a53913,0x3b77bbfa,
0x3b0ebbf6,0xba8a38ec,0x378bae46,0x389bba4f,0x34a5b913,0xbbff3b99,0x3ba8ba2f,0x2648b505,0xb78b2e46,0xbac23bb6,0x3b0ebbf6,0xb8483444,
0xb81d395f,0x3bf1bbff,0xbadd39ed,0x2fd6a648,0xb0b23564,0x3b99bbce,0xbbea3b88,0x3505b303,0x33c6aa48,0x3af6bb50,0xbbc33bfe,0x37e3b67c,
0x38c4b6d7,0x3a0fba8a,0xba6d3b3b,0x393ab89b,0xb9a839a8,0xafd62648,0x39a8b9a8,0xbbf13bff,0xb9a839a8,0xb5053303,0x39a8b9a8,0xbb993bce,
0xb9a839a8,0xb7e3367c,0x39a8b9a8,0xbaf63b50,0xb9a839a8,0xb93a389b,0x39a8b9a8,0xba0f3a8a,0x3addb9ed,0xbb773bfa,0x381db95f,0x35c2acb5,
0x3beabb88,0xb89b3a4f,0x30b2b564,0x3a8ab8ec,0x3bc3bbfe,0xa6483505,0xb3c62a48,0x3bffbb99,0x3a6dbb3b,0x3848b444,0xb8c436d7,0x3ac2bbb6,
0x34a5b913,0x389bafd6,0xbba83a2f,0x3a8abbf1,0xb78b2e46,0x3bffbb25,0xbb0e3bf6,0xa648b732,0xbba83a2f,0x3848baf6,0xb4a53913,0xbac237e3,
0xbb0e3bf6,0xb67cacb5,0x378bae46,0xbb503bfa,0xbbfe3a6d,0x393abbe2,0xaa4838c4,0xba0f3179,0xb6d73add,0xb8eca648,0x3b3bb81d,0xba4f3bff,
0x395fb0b2,0xbb253bce,0x39edbbea,0x37323303,0x3b88bbc3,0x3444367c,0xb564b3c6,0x3bb6bb50,0x323e3872,0xbb253303,0x3bd9baa7,0xb7323bce,
0x3bd9baa7,0xb4443b50,0xb23eb872,0x3bb6b67c,0xb23eb872,0x3bfab89b,0xbbd93aa7,0x2cb5ba8a,0xbbd93aa7,0xafd6b984,0x323e3872,0xbbf139cb,
0x3b3bbadd,0xb3033bb6,0xb6d7b81d,0x3bceb444,0xb9edb0b2,0x3b77ba0f,0xb95f3bea,0xb5c2b93a,0xb5643bc3,0xba8aafd6,0x3b88b3c6,0xb89b3bf1,
0x3bfeb8c4,0xa6483b25,0xaa48ba6d,0x3bffb732,0xb913b78b,0x3bffb505,0xba2f3b0e,0xa648bb99,0xae463ba8,0xbac2b444,0x3bf6b4a5,0xb8483bb6,
0x3a2fbb0e,0x367c3a0f,0xb913b78b,0x3b50b93a,0xbbf634a5,0x3179bbf1,0xae463ba8,0xbbe22fd6,0xb8c43b3b,0xb444bb77,0x3a6d36d7,0xbbb635c2,
0x3addb95f,0x2cb53be2,0xb81db9ed,0x3bfab179,0xbbea3564,0x2fd6bbff,0x30b23b88,0xbbf1a648,0x3bc32a48,0xb5053bce,0x33c6bbfe,0x3b993303,
0x3b64361f,0xbaf6367c,0x361fbb64,0x37e33b50,0xbb64b61f,0x3a0fb89b,0xb61f3b64,0xb93aba8a,0x3b64361f,0xb8ec39cb,0x361fbb64,0x3a4f3984,
0xbb64b61f,0x3732bac2,0xb61f3b64,0xbb25b848,0x30b2bb88,0x39843b25,0xbbeab564,0x39cbb732,0x33c63bfe,0xbbceb7e3,0x3bc3aa48,0xb3033af6,
0xb8c4bb3b,0x3b77acb5,0xba6d36d7,0xb5c2bbfa,0x3add395f,0xb89b38ec,0x381db9ed,0x3a8a3a4f,0xbbf6b4a5,0x3848b7e3,0x2e463ba8,0xbac2baf6,
0x3913b78b,0x367c3bfa,0xba2fbb0e,0x3b502cb5,0x2e463ba8,0xbbe2b8ec,0x3bf634a5,0xb1793a4f,0xba2fbb0e,0x3984b505,0xb913378b,0xb9cbbb99,
0x35643bc3,0xbb99bac2,0x3b8833c6,0xb5053848,0xbbfeb8c4,0x37e3b5c2,0xaa483a6d,0xbaf6bb77,0x36d7b81d,0x3a0f3be2,0xbb3bbadd,0x393ab179,
0x395f3bea,0xba4fa648,0x39edb0b2,0x38ec3bff,0x3aa7323e,0xacb5389b,0xb872bbd9,0x3bfa3a8a,0x38723bd9,0xbbf1b984,0x3aa7323e,0x2fd639cb,
0xbaa7b23e,0xb505bac2,0x38723bd9,0xbb99b848,0xb872bbd9,0x3af635c2,0xbaa7b23e,0xb7e3bb77,0xb9edbbea,0x3be23a4f,0xb95fb0b2,0xb179b8ec,
0x3564b3c6,0x39843b99,0xbb88bbc3,0x39cb3505,0x3bfe3a6d,0xb3033444,0xaa48b8c4,0x3bce3bb6,0x36d73add,0xbb77b93a,0x3b3b381d,0x35c23a0f,
0xb78bae46,0xb67cb93a,0x3b0e3bf6,0xbb50ba0f,0xbba8ba2f,0x3179afd6,0x34a53913,0xbbe2bbf1,0xbb0ebbf6,0x39843732,0xb78bae46,0xb9cbbb25,
0xb4a5b913,0x3bce3af6,0xbba8ba2f,0xb303b7e3,0x3bc33bfe,0xba4fb9cb,0x33c62a48,0x38ec3984,0x3a6d3b3b,0xbb25bac2,0x38c436d7,0x37323848,
0x381d395f,0xbbb6bb77,0x3add39ed,0x344435c2,0x30b23564,0xbbfabbe2,0x3bea3b88,0x2cb53179,0x3c003c00,0xafd6a648,0,0xbbf1bbff,
0x3c003c00,0xb505b303,0,0xbb99bbce,0x3c003c00,0xb7e3b67c,0,0xbaf6bb50,0x3c003c00,0xb93ab89b,0,0xba0fba8a,
0xbbc3bbfe,0x35c22cb5,0x33c62a48,0x3b773bfa,0xba6dbb3b,0x3a8a38ec,0x38c436d7,0x389b3a4f,0xb81db95f,0x3bff3b99,0x3add39ed,0x26483505,
0xb0b2b564,0x3ac23bb6,0x3bea3b88,0xb848b444,0x3b0e3bf6,0xb89bafd6,0xb78bae46,0xba8abbf1,0x34a53913,0xbbffbb25,0xbba8ba2f,0x2648b732,
0xb78bae46,0xb848baf6,0xbb0ebbf6,0x3ac237e3,0xbba8ba2f,0x367cacb5,0xb4a5b913,0x3b503bfa,0xb9edbbea,0x3a0f3179,0x395f30b2,0x393a3be2,
0x3564b3c6,0x3a4f3bff,0x3b883bc3,0xb8ec2648,0x3bfe3a6d,0xb7323303,0x2a4838c4,0xbb25bbce,0x36d73add,0xbbb6bb50,0xbb3bb81d,0x3444b67c,
0x38723bd9,0xbb25b303,0xbaa7b23e,0xb732bbce,0xbaa7b23e,0xb444bb50,0xb872bbd9,0x3bb6367c,0xb872bbd9,0x3bfa389b,0x3aa7323e,0x2cb53a8a,
0x3aa7323e,0xafd63984,0x38723bd9,0xbbf1b9cb,0xb564bbc3,0x3bce3444,0x3b8833c6,0x33033bb6,0x3bfe38c4,0xb5c2393a,0xaa483a6d,0xbb77ba0f,
0xb6d7381d,0xb89bbbf1,0xbb3bbadd,0x3a8aafd6,0xb95fbbea,0x3bff3732,0x39edb0b2,0x26483b25,0x2e463ba8,0xbbffb505,0xbbf6b4a5,0x2648bb99,
0xba2fbb0e,0x3ac2b444,0x3913b78b,0x38483bb6,0x3bf634a5,0xb67c3a0f,0x2e463ba8,0xbb50b93a,0xb913378b,0xb179bbf1,0xba2fbb0e,0x3be22fd6,
0x30b2bb88,0x3bb635c2,0x3bea3564,0xb4443b77,0x33c63bfe,0xbbfab179,0xbbc32a48,0x2cb5bbe2,0xb8c4bb3b,0x3bf1a648,0x3a6db6d7,0x2fd63bff,
0x3add395f,0xbb993303,0xb81d39ed,0xb505bbce,0xb61f3b64,0xbaf6b67c,0xbb64b61f,0x37e3bb50,0x361fbb64,0x3a0f389b,0x3b64361f,0xb93a3a8a,
0xb61f3b64,0xb8ecb9cb,0xbb64b61f,0x3a4fb984,0x361fbb64,0x37323ac2,0x3b64361f,0xbb253848,0x38c4bb3b,0x39cb3732,0x3a6d36d7,0xb9843b25,
0xbadd395f,0xb303baf6,0xb81db9ed,0x3bceb7e3,0x3beab564,0xb5c23bfa,0x30b23b88,0xbb77acb5,0xbbc3aa48,0x3a8aba4f,0x33c6bbfe,0x389b38ec,
0xba2f3b0e,0xb848b7e3,0xb913b78b,0x3ac2baf6,0x3bf6b4a5,0xb67c3bfa,0xae463ba8,0xbb502cb5,0xb913b78b,0x3be2b8ec,0x3a2fbb0e,0x31793a4f,
0xae463ba8,0xb984b505,0xbbf634a5,0x39cbbb99,0x3b3bbadd,0x35053848,0x36d7381d,0xbb993ac2,0xb9edb0b2,0x3af6bb77,0x395fbbea,0x37e335c2,
0xb5643bc3,0xb93ab179,0xbb8833c6,0x3a0fbbe2,0x3bfeb8c4,0xb8ec3bff,0x2a483a6d,0xba4f2648,0xbbd93aa7,0xacb5b89b,0xb23eb872,0x3bfaba8a,
0x323e3872,0xbbf13984,0xbbd93aa7,0x2fd6b9cb,0x3bd9baa7,0xb5053ac2,0x323e3872,0xbb993848,0xb23eb872,0x3af6b5c2,0x3bd9baa7,0xb7e33b77,
0x3bfeba6d,0xb17938ec,0xaa4838c4,0xbbe23a4f,0x36d7badd,0x39cbb505,0x3b3bb81d,0xb9843b99,0xb95f30b2,0x3bcebbb6,0x39edbbea,0x33033444,
0xbb883bc3,0x35c2ba0f,0xb564b3c6,0x3b77b93a,0xbba83a2f,0x367cb93a,0x34a5b913,0x3b50ba0f,0xbb0e3bf6,0xb179afd6,0xb78b2e46,0x3be2bbf1,
0xb4a53913,0xb9843732,0xbba83a2f,0x39cbbb25,0x378bae46,0xbbce3af6,0xbb0e3bf6,0x3303b7e3,0x3addb9ed,0xb8ec3984,0xb81d395f,0xba4f39cb,
0x3beabb88,0xb7323848,0xb0b23564,0xbb253ac2,0x3bc3bbfe,0xb44435c2,0x33c6aa48,0xbbb63b77,0x3a6dbb3b,0xacb53179,0x38c4b6d7,0xbbfa3be2,
0xb9a839a8,0x3a4fb9cb,0x39a8b9a8,0x38ecb984,0xb9a839a8,0x3b25bac2,0x39a8b9a8,0x3732b848,0xb9a839a8,0x3bb6bb77,0x39a8b9a8,0x3444b5c2,
0xb9a839a8,0x3bfabbe2,0x39a8b9a8,0x2cb5b179,0x381db95f,0xbb503a0f,0xbadd39ed,0xb67c393a,0x30b2b564,0xbbe23bf1,0xbbea3b88,0x31792fd6,
0xb3c62a48,0xb9cb3b25,0xbbc33bfe,0x3984b732,0xb8c436d7,0xb30337e3,0xba6d3b3b,0x3bcebaf6,0xb4a53913,0x3be2ba4f,0x3ba8ba2f,0x3179b8ec,
0x378bae46,0x3984bb99,0x3b0ebbf6,0xb9cb3505,0x3ba8ba2f,0xb303b444,0x34a5b913,0xbbce3bb6,0x3b0ebbf6,0xbb77393a,0xb78b2e46,0xb5c23a0f,
0x2a48b8c4,0xbbfa3a8a,0xbbfe3a6d,0x2cb5389b,0xbb3b381d,0xafd639cb,0xb6d73add,0x3bf1b984,0xb9ed3bea,0x3b99b848,0x395fb0b2,0x3505bac2,
0x356433c6,0x37e3bb77,0x3b88bbc3,0xbaf635c2,0x323e3872,0x3b99bac2,0x3bd9baa7,0xb505b848,0x3bd9baa7,0xb7e3b5c2,0xb23eb872,0xbaf63b77,
0xb23eb872,0xba0f3be2,0xbbd93aa7,0x393a3179,0xbbd93aa7,0x3a4fa648,0x323e3872,0x38ecbbff,0xb6d7b81d,0xbac23af6,0xbb3b3add,0x384837e3,
0xb95f3bea,0x3b50acb5,0x39ed30b2,0x367cbbfa,0x3b88b3c6,0xb179ba4f,0x3564bbc3,0xbbe238ec,0xaa48ba6d,0xb9cb3b99,0xbbfe38c4,0x39843505,
0x3913378b,0x3984bb25,0x3a2fbb0e,0xb9cbb732,0x2e46bba8,0xbbce37e3,0xbbf634a5,0x33033af6,0xba2f3b0e,0x3b772cb5,0x3913378b,0x35c2bbfa,
0x3bf6b4a5,0xb89bb8ec,0x2e46bba8,0xba8a3a4f,0xba6db6d7,0xb7e33b50,0xb8c43b3b,0x3af6367c,0x381d39ed,0x393aba8a,0x3addb95f,0xba0fb89b,
0xb0b2bb88,0xba4f3984,0xbbea3564,0x38ec39cb,0xb3c63bfe,0x3b25b848,0x3bc32a48,0xb732bac2,0x3b64361f,0x3444bb77,0x361fbb64,0xbbb6b5c2,
0xbb64b61f,0xacb53be2,0xb61f3b64,0x3bfa3179,0x3b64361f,0xafd6bbff,0x361fbb64,0xbbf12648,0xbb64b61f,0x35053bce,0xb61f3b64,0x3b99b303,
0xbbeab564,0xa6483b99,0xb0b23b88,0x3bff3505,0x3bc3aa48,0xb848bbb6,0xb3c6bbfe,0xbac23444,0xba6d36d7,0x3b50393a,0x38c43b3b,0x367cba0f,
0x381db9ed,0xbbe2afd6,0xbaddb95f,0x31793bf1,0x3bf634a5,0xb303bbb6,0xae46bba8,0xbbceb444,0xb913378b,0x3b773a0f,0x3a2f3b0e,0x35c2b93a,
0xae46bba8,0xba8a2fd6,0xbbf6b4a5,0x389b3bf1,0x3a2f3b0e,0xa648bb25,0x3913b78b,0xbbffb732,0xbb88b3c6,0x37323bce,0x35643bc3,0x3b253303,
0x2a48ba6d,0xbbb6b67c,0xbbfeb8c4,0x34443b50,0x3b3b3add,0xacb5ba8a,0x36d7b81d,0xbbfab89b,0xb9ed30b2,0x3bf139cb,0x395f3bea,0x2fd6b984,
0x3aa7323e,0xb93abbe2,0xb872bbd9,0xba0fb179,0x38723bd9,0x38eca648,0x3aa7323e,0xba4fbbff,0xbaa7b23e,0x3b253bce,0x38723bd9,0x3732b303,
0xb872bbd9,0xb444367c,0xbaa7b23e,0x3bb63b50,0xb95fb0b2,0x3a8a3bf1,0x39ed3bea,0x389b2fd6,0xbb88bbc3,0xa6483732,0xb56433c6,0x3bff3b25,
0xaa48b8c4,0xbac2b7e3,0xbbfeba6d,0x38483af6,0x3b3b381d,0xbb50bbfa,0xb6d7badd,0xb67c2cb5,0x378b2e46,0xbb77bbfa,0xbb0ebbf6,0xb5c2acb5,
0x3ba83a2f,0xb89bba4f,0xb4a5b913,0xba8ab8ec,0x3b0e3bf6,0xa648b505,0x378b2e46,0xbbffbb99,0x34a53913,0x38483444,0x3ba83a2f,0xbac2bbb6,
0xb3c6aa48,0x3bf13bff,0x3bc33bfe,0x2fd62648,0xb8c4b6d7,0x3b993bce,0x3a6d3b3b,0x35053303,0xbaddb9ed,0x3af63b50,0x381d395f,0x37e3367c,
0xbbeabb88,0x3a0f3a8a,0x30b23564,0x393a389b,0x3c003c00,0x2fd62648,0,0x3bf13bff,0x3c003c00,0x35053303,0,0x3b993bce,
0x3c003c00,0x37e3367c,0,0x3af63b50,0x3c003c00,0x393a389b,0,0x3a0f3a8a,0xbbc3bbfe,0xb5c2acb5,0x33c62a48,0xbb77bbfa,
0xba6dbb3b,0xba8ab8ec,0x38c436d7,0xb89bba4f,0xb81db95f,0xbbffbb99,0x3add39ed,0xa648b505,0xb0b2b564,0xbac2bbb6,0x3bea3b88,0x38483444,
0x3b0e3bf6,0x389b2fd6,0xb78bae46,0x3a8a3bf1,0x34a53913,0x3bff3b25,0xbba8ba2f,0xa6483732,0xb78bae46,0x38483af6,0xbb0ebbf6,0xbac2b7e3,
0xbba8ba2f,0xb67c2cb5,0xb4a5b913,0xbb50bbfa,0xb9edbbea,0xba0fb179,0x395f30b2,0xb93abbe2,0x3564b3c6,0xba4fbbff,0x3b883bc3,0x38eca648,
0x3bfe3a6d,0x3732b303,0x2a4838c4,0x3b253bce,0x36d73add,0x3bb63b50,0xbb3bb81d,0xb444367c,0x38723bd9,0x3b253303,0xbaa7b23e,0x37323bce,
0xbaa7b23e,0x34443b50,0xb872bbd9,0xbbb6b67c,0xb872bbd9,0xbbfab89b,0x3aa7323e,0xacb5ba8a,0x3aa7323e,0x2fd6b984,0x38723bd9,0x3bf139cb,
0xb564bbc3,0xbbceb444,0x3b8833c6,0xb303bbb6,0x3bfe38c4,0x35c2b93a,0xaa483a6d,0x3b773a0f,0xb6d7381d,0x389b3bf1,0xbb3bbadd,0xba8a2fd6,
0xb95fbbea,0xbbffb732,0x39edb0b2,0xa648bb25,0x2e463ba8,0x3bff3505,0xbbf6b4a5,0xa6483b99,0xba2fbb0e,0xbac23444,0x3913b78b,0xb848bbb6,
0x3bf634a5,0x367cba0f,0x2e463ba8,0x3b50393a,0xb913378b,0x31793bf1,0xba2fbb0e,0xbbe2afd6,0x30b2bb88,0xbbb6b5c2,0x3bea3564,0x3444bb77,
0x33c63bfe,0x3bfa3179,0xbbc32a48,0xacb53be2,0xb8c4bb3b,0xbbf12648,0x3a6db6d7,0xafd6bbff,0x3add395f,0x3b99b303,0xb81d39ed,0x35053bce,
0xb61f3b64,0x3af6367c,0xbb64b61f,0xb7e33b50,0x361fbb64,0xba0fb89b,0x3b64361f,0x393aba8a,0xb61f3b64,0x38ec39cb,0xbb64b61f,0xba4f3984,
0x361fbb64,0xb732bac2,0x3b64361f,0x3b25b848,0x38c4bb3b,0xb9cbb732,0x3a6d36d7,0x3984bb25,0xbadd395f,0x33033af6,0xb81db9ed,0xbbce37e3,
0x3beab564,0x35c2bbfa,0x30b23b88,0x3b772cb5,0xbbc3aa48,0xba8a3a4f,0x33c6bbfe,0xb89bb8ec,0xba2f3b0e,0x384837e3,0xb913b78b,0xbac23af6,
0x3bf6b4a5,0x367cbbfa,0xae463ba8,0x3b50acb5,0xb913b78b,0xbbe238ec,0x3a2fbb0e,0xb179ba4f,0xae463ba8,0x39843505,0xbbf634a5,0xb9cb3b99,
0x3b3bbadd,0xb505b848,0x36d7381d,0x3b99bac2,0xb9edb0b2,0xbaf63b77,0x395fbbea,0xb7e3b5c2,0xb5643bc3,0x393a3179,0xbb8833c6,0xba0f3be2,
0x3bfeb8c4,0x38ecbbff,0x2a483a6d,0x3a4fa648,0xbbd93aa7,0x2cb5389b,0xb23eb872,0xbbfa3a8a,0x323e3872,0x3bf1b984,0xbbd93aa7,0xafd639cb,
0x3bd9baa7,0x3505bac2,0x323e3872,0x3b99b848,0xb23eb872,0xbaf635c2,0x3bd9baa7,0x37e3bb77,0x3bfeba6d,0x3179b8ec,0xaa4838c4,0x3be2ba4f,
0x36d7badd,0xb9cb3505,0x3b3bb81d,0x3984bb99,0xb95f30b2,0xbbce3bb6,0x39edbbea,0xb303b444,0xbb883bc3,0xb5c23a0f,0xb564b3c6,0xbb77393a,
0xbba83a2f,0xb67c393a,0x34a5b913,0xbb503a0f,0xbb0e3bf6,0x31792fd6,0xb78b2e46,0xbbe23bf1,0xb4a53913,0x3984b732,0xbba83a2f,0xb9cb3b25,
0x378bae46,0x3bcebaf6,0xbb0e3bf6,0xb30337e3,0x3addb9ed,0x38ecb984,0xb81d395f,0x3a4fb9cb,0x3beabb88,0x3732b848,0xb0b23564,0x3b25bac2,
0x3bc3bbfe,0x3444b5c2,0x33c6aa48,0x3bb6bb77,0x3a6dbb3b,0x2cb5b179,0x38c4b6d7,0x3bfabbe2,0xb9a839a8,0xba4f39cb,0x39a8b9a8,0xb8ec3984,
0xb9a839a8,0xbb253ac2,0x39a8b9a8,0xb7323848,0xb9a839a8,0xbbb63b77,0x39a8b9a8,0xb44435c2,0xb9a839a8,0xbbfa3be2,0x39a8b9a8,0xacb53179,
0x381db95f,0x3b50ba0f,0xbadd39ed,0x367cb93a,0x30b2b564,0x3be2bbf1,0xbbea3b88,0xb179afd6,0xb3c62a48,0x39cbbb25,0xbbc33bfe,0xb9843732,
0xb8c436d7,0x3303b7e3,0xba6d3b3b,0xbbce3af6,0xb4a53913,0xbbe23a4f,0x3ba8ba2f,0xb17938ec,0x378bae46,0xb9843b99,0x3b0ebbf6,0x39cbb505,
0x3ba8ba2f,0x33033444,0x34a5b913,0x3bcebbb6,0x3b0ebbf6,0x3b77b93a,0xb78b2e46,0x35c2ba0f,0x2a48b8c4,0x3bfaba8a,0xbbfe3a6d,0xacb5b89b,
0xbb3b381d,0x2fd6b9cb,0xb6d73add,0xbbf13984,0xb9ed3bea,0xbb993848,0x395fb0b2,0xb5053ac2,0x356433c6,0xb7e33b77,0x3b88bbc3,0x3af6b5c2,
0x323e3872,0xbb993ac2,0x3bd9baa7,0x35053848,0x3bd9baa7,0x37e335c2,0xb23eb872,0x3af6bb77,0xb23eb872,0x3a0fbbe2,0xbbd93aa7,0xb93ab179,
0xbbd93aa7,0xba4f2648,0x323e3872,0xb8ec3bff,0xb6d7b81d,0x3ac2baf6,0xbb3b3add,0xb848b7e3,0xb95f3bea,0xbb502cb5,0x39ed30b2,0xb67c3bfa,
0x3b88b3c6,0x31793a4f,0x3564bbc3,0x3be2b8ec,0xaa48ba6d,0x39cbbb99,0xbbfe38c4,0xb984b505,0x3913378b,0xb9843b25,0x3a2fbb0e,0x39cb3732,
0x2e46bba8,0x3bceb7e3,0xbbf634a5,0xb303baf6,0xba2f3b0e,0xbb77acb5,0x3913378b,0xb5c23bfa,0x3bf6b4a5,0x389b38ec,0x2e46bba8,0x3a8aba4f,
0xba6db6d7,0x37e3bb50,0xb8c43b3b,0xbaf6b67c,0x381d39ed,0xb93a3a8a,0x3addb95f,0x3a0f389b,0xb0b2bb88,0x3a4fb984,0xbbea3564,0xb8ecb9cb,
0xb3c63bfe,0xbb253848,0x3bc32a48,0x37323ac2,0x3b64361f,0xb4443b77,0x361fbb64,0x3bb635c2,0xbb64b61f,0x2cb5bbe2,0xb61f3b64,0xbbfab179,
0x3b64361f,0x2fd63bff,0x361fbb64,0x3bf1a648,0xbb64b61f,0xb505bbce,0xb61f3b64,0xbb993303,0xbbeab564,0x2648bb99,0xb0b23b88,0xbbffb505,
0x3bc3aa48,0x38483bb6,0xb3c6bbfe,0x3ac2b444,0xba6d36d7,0xbb50b93a,0x38c43b3b,0xb67c3a0f,0x381db9ed,0x3be22fd6,0xbaddb95f,0xb179bbf1,
0x3bf634a5,0x33033bb6,0xae46bba8,0x3bce3444,0xb913378b,0xbb77ba0f,0x3a2f3b0e,0xb5c2393a,0xae46bba8,0x3a8aafd6,0xbbf6b4a5,0xb89bbbf1,
0x3a2f3b0e,0x26483b25,0x3913b78b,0x3bff3732,0xbb88b3c6,0xb732bbce,0x35643bc3,0xbb25b303,0x2a48ba6d,0x3bb6367c,0xbbfeb8c4,0xb444bb50,
0x3b3b3add,0x2cb53a8a,0x36d7b81d,0x3bfa389b,0xb9ed30b2,0xbbf1b9cb,0x395f3bea,0xafd63984,0x3aa7323e,0x393a3be2,0xb872bbd9,0x3a0f3179,
0x38723bd9,0xb8ec2648,0x3aa7323e,0x3a4f3bff,0xbaa7b23e,0xbb25bbce,0x38723bd9,0xb7323303,0xb872bbd9,0x3444b67c,0xbaa7b23e,0xbbb6bb50,
0xb95fb0b2,0xba8abbf1,0x39ed3bea,0xb89bafd6,0xbb88bbc3,0x2648b732,0xb56433c6,0xbbffbb25,0xaa48b8c4,0x3ac237e3,0xbbfeba6d,0xb848baf6,
0x3b3b381d,0x3b503bfa,0xb6d7badd,0x367cacb5,0x378b2e46,0x3b773bfa,0xbb0ebbf6,0x35c22cb5,0x3ba83a2f,0x389b3a4f,0xb4a5b913,0x3a8a38ec,
0x3b0e3bf6,0x26483505,0x378b2e46,0x3bff3b99,0x34a53913,0xb848b444,0x3ba83a2f,0x3ac23bb6,0xb3c6aa48,0xbbf1bbff,0x3bc33bfe,0xafd6a648,
0xb8c4b6d7,0xbb99bbce,0x3a6d3b3b,0xb505b303,0xbaddb9ed,0xbaf6bb50,0x381d395f,0xb7e3b67c,0xbbeabb88,0xba0fba8a,0x30b23564,0xb93ab89b,
0x3c003c00,0xba4fb9cb,0,0xb8ecb984,0x3c003c00,0xbb25bac2,0,0xb732b848,0x3c003c00,0xbbb6bb77,0,0xb444b5c2,
0x3c003c00,0xbbfabbe2,0,0xacb5b179,0x33c62a48,0x367c393a,0x3bc33bfe,0xbb50ba0f,0x38c436d7,0xb1792fd6,0x3a6d3b3b,0xbbe2bbf1,
0x3add39ed,0xb984b732,0x381d395f,0xb9cbbb25,0x3bea3b88,0xbbcebaf6,0x30b23564,0xb303b7e3,0xbb0ebbf6,0x3be23a4f,0x378b2e46,0x317938ec,
0xb4a5b913,0x39843b99,0x3ba83a2f,0xb9cbb505,0x378b2e46,0xb3033444,0x3b0e3bf6,0xbbcebbb6,0x3ba83a2f,0xbb77b93a,0x34a53913,0xb5c2ba0f,
0xb95fb0b2,0x2cb5b89b,0xb9edbbea,0x3bfa3a8a,0xbb88bbc3,0x3bf13984,0x3564b3c6,0x2fd639cb,0xaa48b8c4,0x35053ac2,0x3bfe3a6d,0xbb99b848,
0x3b3b381d,0xbaf6b5c2,0x36d73add,0xb7e3bb77,0x38723bd9,0xbb99bac2,0xbaa7b23e,0x3505b848,0xbaa7b23e,0x37e3b5c2,0xb872bbd9,0x3af63b77,
0xb872bbd9,0x3a0f3be2,0x3aa7323e,0xb93a3179,0x3aa7323e,0xba4fa648,0x38723bd9,0xb8ecbbff,0x3b8833c6,0xb84837e3,0x35643bc3,0xbac2baf6,
0xaa483a6d,0xb67cbbfa,0xbbfeb8c4,0x3b502cb5,0xbb3bbadd,0x3be238ec,0x36d7b81d,0xb1793a4f,0x39edb0b2,0xb9843505,0x395f3bea,0xb9cbbb99,
0xae46bba8,0x39843b25,0x3bf634a5,0xb9cb3732,0x3a2f3b0e,0xbbceb7e3,0xb913378b,0x3303baf6,0xbbf6b4a5,0x3b77acb5,0xae46bba8,0x35c23bfa,
0x3913b78b,0xb89b38ec,0x3a2f3b0e,0xba8aba4f,0xbbeab564,0x3af6b67c,0x30b2bb88,0x37e33b50,0x3bc3aa48,0xba0f389b,0x33c63bfe,0xb93aba8a,
0xba6d36d7,0x38ecb9cb,0xb8c4bb3b,0x3a4f3984,0x381db9ed,0xb7323ac2,0x3add395f,0xbb25b848,0xb61f3b64,0xb444bb77,0xbb64b61f,0x3bb6b5c2,
0x361fbb64,0x2cb53be2,0x3b64361f,0xbbfa3179,0xb61f3b64,0x2fd6bbff,0xbb64b61f,0x3bf12648,0x361fbb64,0xb5053bce,0x3b64361f,0xbb99b303,
0x3a6d36d7,0xbbff3505,0xb8c43b3b,0xa648bb99,0xb81db9ed,0x3ac23444,0x3addb95f,0xb8483bb6,0x30b23b88,0xb67cba0f,0xbbea3564,0x3b50b93a,
0x33c6bbfe,0xb1793bf1,0x3bc32a48,0xbbe22fd6,0x3a2fbb0e,0xb3033bb6,0x3913378b,0xbbce3444,0xbbf634a5,0x3b77ba0f,0x2e46bba8,0x35c2393a,
0x3913378b,0xba8aafd6,0xba2f3b0e,0x389bbbf1,0x2e46bba8,0xa6483b25,0x3bf6b4a5,0xbbff3732,0xb6d7b81d,0x3b25b303,0x3b3bbadd,0xb7323bce,
0xb95f3bea,0x3444bb50,0xb9edb0b2,0x3bb6b67c,0x3b88b3c6,0xbbfa389b,0xb5643bc3,0x2cb5ba8a,0xaa48ba6d,0x2fd63984,0x3bfeb8c4,0xbbf139cb,
0xbbd93aa7,0x393abbe2,0xb23eb872,0x3a0fb179,0x323e3872,0xb8eca648,0xbbd93aa7,0x3a4fbbff,0x3bd9baa7,0xbb253bce,0x323e3872,0xb732b303,
0xb23eb872,0x3444367c,0x3bd9baa7,0xbbb63b50,0xaa4838c4,0xb89b2fd6,0xbbfe3a6d,0x3a8abbf1,0x3b3bb81d,0xbbff3b25,0xb6d73add,0xa648b732,
0x39edbbea,0xb8483af6,0x395fb0b2,0xbac237e3,0xb564b3c6,0x367c2cb5,0x3b88bbc3,0xbb503bfa,0x3ba8ba2f,0xbb773bfa,0xb4a53913,0xb5c22cb5,
0x3b0ebbf6,0xb89b3a4f,0x378bae46,0xba8a38ec,0x34a5b913,0xa6483505,0x3ba8ba2f,0xbbff3b99,0xb78b2e46,0x3848b444,0x3b0ebbf6,0xbac23bb6,
0x381db95f,0x2fd6a648,0x3addb9ed,0xbbf13bff,0x30b2b564,0x3505b303,0x3beabb88,0xbb993bce,0xb3c62a48,0x37e3b67c,0x3bc3bbfe,0xbaf63b50,
0xb8c436d7,0x393ab89b,0x3a6dbb3b,0xba0f3a8a,0xb9a839a8,0x3bf1bbff,0x39a8b9a8,0xafd62648,0xb9a839a8,0x3b99bbce,0x39a8b9a8,0xb5053303,
0xb9a839a8,0x3af6bb50,0x39a8b9a8,0xb7e3367c,0xb9a839a8,0x3a0fba8a,0x39a8b9a8,0xb93a389b,0xbadd39ed,0x35c2acb5,0xb81d395f,0x3b77bbfa,
0xbbea3b88,0x3a8ab8ec,0xb0b23564,0x389bba4f,0xbbc33bfe,0x3bffbb99,0x33c6aa48,0x2648b505,0xba6d3b3b,0x3ac2bbb6,0x38c4b6d7,0xb8483444,
0x34a5b913,0xba8a3bf1,0xbba83a2f,0x389bafd6,0xb78b2e46,0x26483732,0xbb0e3bf6,0x3bffbb25,0xbba83a2f,0x3ac2b7e3,0xb4a53913,0x3848baf6,
0xbb0e3bf6,0x3b50bbfa,0x378bae46,0xb67cacb5,0x3bfeba6d,0xba0f3179,0x2a48b8c4,0xb93a3be2,0x36d7badd,0xba4f3bff,0xbb3b381d,0x38ec2648,
0xb95f30b2,0x37323303,0xb9ed3bea,0x3b25bbce,0xbb883bc3,0x3bb6bb50,0x356433c6,0xb444b67c,0x323e3872,0x3732bbce,0x3bd9baa7,0xbb253303,
0x3bd9baa7,0xbbb6367c,0xb23eb872,0xb4443b50,0xb23eb872,0xacb53a8a,0xbbd93aa7,0x3bfab89b,0xbbd93aa7,0x3bf1b9cb,0x323e3872,0xafd6b984,
0xbb3b3add,0x3bceb444,0x36d7381d,0x3303bbb6,0x39ed30b2,0xb5c2b93a,0x395fbbea,0xbb773a0f,0x3564bbc3,0xb89b3bf1,0xbb8833c6,0x3a8a2fd6,
0xbbfe38c4,0x3bffb732,0x2a483a6d,0x2648bb25,0xb913b78b,0x26483b99,0xba2f3b0e,0x3bffb505,0xae463ba8,0x3848bbb6,0x3bf6b4a5,0xbac2b444,
0x3a2fbb0e,0xbb50393a,0xb913b78b,0x367c3a0f,0xbbf634a5,0x3be2afd6,0xae463ba8,0x3179bbf1,0x38c4bb3b,0xbbb635c2,0xba6db6d7,0x34443b77,
0xbadd395f,0x3bfab179,0x381d39ed,0xacb5bbe2,0x3beab564,0xbbf1a648,0xb0b2bb88,0xafd63bff,0xbbc3aa48,0x3b993303,0xb3c63bfe,0x3505bbce,
0x3b64361f,0xb7e3bb50,0x361fbb64,0xbaf6367c,0xbb64b61f,0x393a3a8a,0xb61f3b64,0x3a0fb89b,0x3b64361f,0xba4fb984,0x361fbb64,0xb8ec39cb,
0xbb64b61f,0x3b253848,0xb61f3b64,0x3732bac2,0xb0b23b88,0x39cbb732,0x3bea3564,0xb984bb25,0xb3c6bbfe,0xb3033af6,0xbbc32a48,0x3bce37e3,
0x38c43b3b,0xb5c2bbfa,0x3a6db6d7,0xbb772cb5,0xbaddb95f,0x3a8a3a4f,0xb81d39ed,0x389bb8ec,0xbbf6b4a5,0x3ac23af6,0x2e463ba8,0x3848b7e3,
0x3913b78b,0xbb50acb5,0xba2fbb0e,0x367c3bfa,0x2e463ba8,0x3179ba4f,0x3bf634a5,0xbbe2b8ec,0xba2fbb0e,0x39cb3b99,0xb913378b,0x3984b505,
0xb564bbc3,0xb5053848,0xbb88b3c6,0x3b993ac2,0x3bfe38c4,0xbaf6bb77,0x2a48ba6d,0xb7e335c2,0xb6d7381d,0x393ab179,0x3b3b3add,0xba0fbbe2,
0xb95fbbea,0x38ec3bff,0xb9ed30b2,0x3a4f2648,0x3aa7323e,0xbbfaba8a,0xb872bbd9,0xacb5389b,0x38723bd9,0xafd6b9cb,0x3aa7323e,0xbbf1b984,
0xbaa7b23e,0x3b993848,0x38723bd9,0xb505bac2,0xb872bbd9,0x37e33b77,0xbaa7b23e,0x3af635c2,0x39ed3bea,0xb179b8ec,0x395f30b2,0xbbe2ba4f,
0xb56433c6,0x39cb3505,0x3b883bc3,0xb984bb99,0xbbfeba6d,0x3bce3bb6,0x2a4838c4,0x3303b444,0xb6d7badd,0x35c23a0f,0xbb3bb81d,0x3b77393a,
0xb78bae46,0x3b503a0f,0x3b0e3bf6,0xb67cb93a,0xbba8ba2f,0x3be23bf1,0x34a53913,0x3179afd6,0xbb0ebbf6,0x39cb3b25,0xb78bae46,0x39843732,
0xb4a5b913,0x330337e3,0xbba8ba2f,0x3bce3af6,0xbbc3bbfe,0x38ec3984,0xb3c6aa48,0x3a4f39cb,0xba6dbb3b,0x37323848,0xb8c4b6d7,0x3b253ac2,
0xb81db95f,0x344435c2,0xbaddb9ed,0x3bb63b77,0xb0b2b564,0x2cb53179,0xbbeabb88,0x3bfa3be2,0x3c003c00,0x3a4f39cb,0,0x38ec3984,
0x3c003c00,0x3b253ac2,0,0x37323848,0x3c003c00,0x3bb63b77,0,0x344435c2,0x3c003c00,0x3bfa3be2,0,0x2cb53179,
0x33c62a48,0xb67cb93a,0x3bc33bfe,0x3b503a0f,0x38c436d7,0x3179afd6,0x3a6d3b3b,0x3be23bf1,0x3add39ed,0x39843732,0x381d395f,0x39cb3b25,
0x3bea3b88,0x3bce3af6,0x30b23564,0x330337e3,0xbb0ebbf6,0xbbe2ba4f,0x378b2e46,0xb179b8ec,0xb4a5b913,0xb984bb99,0x3ba83a2f,0x39cb3505,
0x378b2e46,0x3303b444,0x3b0e3bf6,0x3bce3bb6,0x3ba83a2f,0x3b77393a,0x34a53913,0x35c23a0f,0xb95fb0b2,0xacb5389b,0xb9edbbea,0xbbfaba8a,
0xbb88bbc3,0xbbf1b984,0x3564b3c6,0xafd6b9cb,0xaa48b8c4,0xb505bac2,0x3bfe3a6d,0x3b993848,0x3b3b381d,0x3af635c2,0x36d73add,0x37e33b77,
0x38723bd9,0x3b993ac2,0xbaa7b23e,0xb5053848,0xbaa7b23e,0xb7e335c2,0xb872bbd9,0xbaf6bb77,0xb872bbd9,0xba0fbbe2,0x3aa7323e,0x393ab179,
0x3aa7323e,0x3a4f2648,0x38723bd9,0x38ec3bff,0x3b8833c6,0x3848b7e3,0x35643bc3,0x3ac23af6,0xaa483a6d,0x367c3bfa,0xbbfeb8c4,0xbb50acb5,
0xbb3bbadd,0xbbe2b8ec,0x36d7b81d,0x3179ba4f,0x39edb0b2,0x3984b505,0x395f3bea,0x39cb3b99,0xae46bba8,0xb984bb25,0x3bf634a5,0x39cbb732,
0x3a2f3b0e,0x3bce37e3,0xb913378b,0xb3033af6,0xbbf6b4a5,0xbb772cb5,0xae46bba8,0xb5c2bbfa,0x3913b78b,0x389bb8ec,0x3a2f3b0e,0x3a8a3a4f,
0xbbeab564,0xbaf6367c,0x30b2bb88,0xb7e3bb50,0x3bc3aa48,0x3a0fb89b,0x33c63bfe,0x393a3a8a,0xba6d36d7,0xb8ec39cb,0xb8c4bb3b,0xba4fb984,
0x381db9ed,0x3732bac2,0x3add395f,0x3b253848,0xb61f3b64,0x34443b77,0xbb64b61f,0xbbb635c2,0x361fbb64,0xacb5bbe2,0x3b64361f,0x3bfab179,
0xb61f3b64,0xafd63bff,0xbb64b61f,0xbbf1a648,0x361fbb64,0x3505bbce,0x3b64361f,0x3b993303,0x3a6d36d7,0x3bffb505,0xb8c43b3b,0x26483b99,
0xb81db9ed,0xbac2b444,0x3addb95f,0x3848bbb6,0x30b23b88,0x367c3a0f,0xbbea3564,0xbb50393a,0x33c6bbfe,0x3179bbf1,0x3bc32a48,0x3be2afd6,
0x3a2fbb0e,0x3303bbb6,0x3913378b,0x3bceb444,0xbbf634a5,0xbb773a0f,0x2e46bba8,0xb5c2b93a,0x3913378b,0x3a8a2fd6,0xba2f3b0e,0xb89b3bf1,
0x2e46bba8,0x2648bb25,0x3bf6b4a5,0x3bffb732,0xb6d7b81d,0xbb253303,0x3b3bbadd,0x3732bbce,0xb95f3bea,0xb4443b50,0xb9edb0b2,0xbbb6367c,
0x3b88b3c6,0x3bfab89b,0xb5643bc3,0xacb53a8a,0xaa48ba6d,0xafd6b984,0x3bfeb8c4,0x3bf1b9cb,0xbbd93aa7,0xb93a3be2,0xb23eb872,0xba0f3179,
0x323e3872,0x38ec2648,0xbbd93aa7,0xba4f3bff,0x3bd9baa7,0x3b25bbce,0x323e3872,0x37323303,0xb23eb872,0xb444b67c,0x3bd9baa7,0x3bb6bb50,
0xaa4838c4,0x389bafd6,0xbbfe3a6d,0xba8a3bf1,0x3b3bb81d,0x3bffbb25,0xb6d73add,0x26483732,0x39edbbea,0x3848baf6,0x395fb0b2,0x3ac2b7e3,
0xb564b3c6,0xb67cacb5,0x3b88bbc3,0x3b50bbfa,0x3ba8ba2f,0x3b77bbfa,0xb4a53913,0x35c2acb5,0x3b0ebbf6,0x389bba4f,0x378bae46,0x3a8ab8ec,
0x34a5b913,0x2648b505,0x3ba8ba2f,0x3bffbb99,0xb78b2e46,0xb8483444,0x3b0ebbf6,0x3ac2bbb6,0x381db95f,0xafd62648,0x3addb9ed,0x3bf1bbff,
0x30b2b564,0xb5053303,0x3beabb88,0x3b99bbce,0xb3c62a48,0xb7e3367c,0x3bc3bbfe,0x3af6bb50,0xb8c436d7,0xb93a389b,0x3a6dbb3b,0x3a0fba8a,
0xb9a839a8,0xbbf13bff,0x39a8b9a8,0x2fd6a648,0xb9a839a8,0xbb993bce,0x39a8b9a8,0x3505b303,0xb9a839a8,0xbaf63b50,0x39a8b9a8,0x37e3b67c,
0xb9a839a8,0xba0f3a8a,0x39a8b9a8,0x393ab89b,0xbadd39ed,0xb5c22cb5,0xb81d395f,0xbb773bfa,0xbbea3b88,0xba8a38ec,0xb0b23564,0xb89b3a4f,
0xbbc33bfe,0xbbff3b99,0x33c6aa48,0xa6483505,0xba6d3b3b,0xbac23bb6,0x38c4b6d7,0x3848b444,0x34a5b913,0x3a8abbf1,0xbba83a2f,0xb89b2fd6,
0xb78b2e46,0xa648b732,0xbb0e3bf6,0xbbff3b25,0xbba83a2f,0xbac237e3,0xb4a53913,0xb8483af6,0xbb0e3bf6,0xbb503bfa,0x378bae46,0x367c2cb5,
0x3bfeba6d,0x3a0fb179,0x2a48b8c4,0x393abbe2,0x36d7badd,0x3a4fbbff,0xbb3b381d,0xb8eca648,0xb95f30b2,0xb732b303,0xb9ed3bea,0xbb253bce,
0xbb883bc3,0xbbb63b50,0x356433c6,0x3444367c,0x323e3872,0xb7323bce,0x3bd9baa7,0x3b25b303,0x3bd9baa7,0x3bb6b67c,0xb23eb872,0x3444bb50,
0xb23eb872,0x2cb5ba8a,0xbbd93aa7,0xbbfa389b,0xbbd93aa7,0xbbf139cb,0x323e3872,0x2fd63984,0xbb3b3add,0xbbce3444,0x36d7381d,0xb3033bb6,
0x39ed30b2,0x35c2393a,0x395fbbea,0x3b77ba0f,0x3564bbc3,0x389bbbf1,0xbb8833c6,0xba8aafd6,0xbbfe38c4,0xbbff3732,0x2a483a6d,0xa6483b25,
0xb913b78b,0xa648bb99,0xba2f3b0e,0xbbff3505,0xae463ba8,0xb8483bb6,0x3bf6b4a5,0x3ac23444,0x3a2fbb0e,0x3b50b93a,0xb913b78b,0xb67cba0f,
0xbbf634a5,0xbbe22fd6,0xae463ba8,0xb1793bf1,0x38c4bb3b,0x3bb6b5c2,0xba6db6d7,0xb444bb77,0xbadd395f,0xbbfa3179,0x381d39ed,0x2cb53be2,
0x3beab564,0x3bf12648,0xb0b2bb88,0x2fd6bbff,0xbbc3aa48,0xbb99b303,0xb3c63bfe,0xb5053bce,0x3b64361f,0x37e33b50,0x361fbb64,0x3af6b67c,
0xbb64b61f,0xb93aba8a,0xb61f3b64,0xba0f389b,0x3b64361f,0x3a4f3984,0x361fbb64,0x38ecb9cb,0xbb64b61f,0xbb25b848,0xb61f3b64,0xb7323ac2,
0xb0b23b88,0xb9cb3732,0x3bea3564,0x39843b25,0xb3c6bbfe,0x3303baf6,0xbbc32a48,0xbbceb7e3,0x38c43b3b,0x35c23bfa,0x3a6db6d7,0x3b77acb5,
0xbaddb95f,0xba8aba4f,0xb81d39ed,0xb89b38ec,0xbbf6b4a5,0xbac2baf6,0x2e463ba8,0xb84837e3,0x3913b78b,0x3b502cb5,0xba2fbb0e,0xb67cbbfa,
0x2e463ba8,0xb1793a4f,0x3bf634a5,0x3be238ec,0xba2fbb0e,0xb9cbbb99,0xb913378b,0xb9843505,0xb564bbc3,0x3505b848,0xbb88b3c6,0xbb99bac2,
0x3bfe38c4,0x3af63b77,0x2a48ba6d,0x37e3b5c2,0xb6d7381d,0xb93a3179,0x3b3b3add,0x3a0f3be2,0xb95fbbea,0xb8ecbbff,0xb9ed30b2,0xba4fa648,
0x3aa7323e,0x3bfa3a8a,0xb872bbd9,0x2cb5b89b,0x38723bd9,0x2fd639cb,0x3aa7323e,0x3bf13984,0xbaa7b23e,0xbb99b848,0x38723bd9,0x35053ac2,
0xb872bbd9,0xb7e3bb77,0xbaa7b23e,0xbaf6b5c2,0x39ed3bea,0x317938ec,0x395f30b2,0x3be23a4f,0xb56433c6,0xb9cbb505,0x3b883bc3,0x39843b99,
0xbbfeba6d,0xbbcebbb6,0x2a4838c4,0xb3033444,0xb6d7badd,0xb5c2ba0f,0xbb3bb81d,0xbb77b93a,0xb78bae46,0xbb50ba0f,0x3b0e3bf6,0x367c393a,
0xbba8ba2f,0xbbe2bbf1,0x34a53913,0xb1792fd6,0xbb0ebbf6,0xb9cbbb25,0xb78bae46,0xb984b732,0xb4a5b913,0xb303b7e3,0xbba8ba2f,0xbbcebaf6,
0xbbc3bbfe,0xb8ecb984,0xb3c6aa48,0xba4fb9cb,0xba6dbb3b,0xb732b848,0xb8c4b6d7,0xbb25bac2,0xb81db95f,0xb444b5c2,0xbaddb9ed,0xbbb6bb77,
0xb0b2b564,0xacb5b179,0xbbeabb88,0xbbfabbe2,0x3c003c00,0x96480000,0x3c003c00,0xa311a248,0x3c003c00,0x9cb69a48,0x3c003c00,0xa452a3db,
0x3c003c00,0x9fdb9e48,0x3c003c00,0xa51ba4b6,0x3c003c00,0xa17fa0b6,0x3bff3c00,0xa5e4a57f,0x3c003c00,0x9fdb0000,0x3bfb3bfc,0xac6aabd9,
0x3bff3c00,0xa5e4a3db,0x3bf93bfa,0xad65ace7,0x3bfe3bff,0xa8e8a7da,0x3bf63bf7,0xae5fade2,0x3bfd3bfe,0xaadea9e3,0x3bf23bf4,0xaf59aedc,
0x3c003c00,0xa3110000,0x3bf03bf4,0xafefaf0e,0x3bfe3bff,0xa94da711,0x3be83bed,0xb0d7b067,0x3bfb3bfd,0xac6aab11,0x3bdf3be4,0xb1b6b147,
0x3bf63bf9,0xae2dad4c,0x3bd43bda,0xb294b226,0x3c003c00,0xa51b0000,0x3bdf3be6,0xb1b6b115,0x3bfc3bfe,0xaba7a91b,0x3bcf3bd7,0xb2f7b257,
0x3bf63bf9,0xae5fad1a,0x3bbc3bc6,0xb41ab396,0x3bec3bf1,0xb074afa4,0x3ba53bb1,0xb4b7b469,0x3bff3c00,0xa6ad0000,0x3bc83bd4,0xb371b2a1,
0x3bfa3bfd,0xad00aaac,0x3bac3bbb,0xb487b420,0x3bef3bf5,0xb029aeaa,0x3b8b3b9d,0xb552b4ed,0x3bde3be7,0xb1cfb0fd,0x3b653b79,0xb61ab5b6,
0x3bff3c00,0xa81f0000,0x3bab3bbc,0xb493b414,0x3bf63bfc,0xae2dac1f,0x3b813b97,0xb58db511,0x3be53bef,0xb122b01d,0x3b4f3b69,0xb682b608,
0x3bcc3bda,0xb328b226,0x3b163b33,0xb76fb6f9,0x3bfe3c00,0xa8e80000,0x3b873ba0,0xb56ab4d5,0x3bf23bfa,0xaf59ace7,0x3b4c3b6b,0xb68db5fd,
0x3bda3be8,0xb219b0e4,0x3b073b2b,0xb7a6b71b,0x3bb73bca,0xb43eb34c,0x3ab63ae0,0xb85ab817,0x3bfe3c00,0xa9b10000,0x3b5e3b80,0xb63cb593,
0x3bee3bf8,0xb042adb0,0x3b103b39,0xb785b6e3,0x3bce3be0,0xb30fb1aa,0x3ab33ae3,0xb85fb812,0x3b9e3bb7,0xb4e7b438,0x3a493a7f,0xb8f3b8ab,
0x3bfd3c00,0xaa7a0000,0x3b2f3b5a,0xb70ab64e,0x3be83bf6,0xb0d7ae78,0x3acb3aff,0xb83ab7c2,0x3bbf3bd6,0xb402b26f,0x3a543a92,0xb8e5b891,
0x3b813ba2,0xb58db4c9,0x39cd3a13,0xb982b935,0x3bfd3c00,0xab430000,0x3afb3b30,0xb7d2b705,0x3be23bf3,0xb16caf40,0x3a7e3abf,0xb8adb84d,
0x3bae3bcb,0xb47bb334,0x39eb3a37,0xb962b909,0x3b603b8a,0xb631b558,0x3946399b,0xba04b9b5,0x3bfc3c00,0xac060000,0x3ac13b02,0xb84ab7b7,
0x3bdc3bf0,0xb201b004,0x3a293a78,0xb91bb8b5,0x3b9c3bc0,0xb4f3b3f7,0x397939d4,0xb9d6b97b,0x3b3d3b70,0xb6d2b5e5,0x38b23918,0xba7aba2b,
0x3bfb3c00,0xac6a0000,0x3a813ad0,0xb8a8b832,0x3bd43bed,0xb294b067,0x39cd3a2b,0xb982b918,0x3b873bb2,0xb56ab45d,0x38fd3969,0xba41b9e5,
0x3b163b53,0xb76fb670,0x3815388c,0xbae1ba95,0x3bfa3c00,0xacce0000,0x3a3d3a99,0xb902b887,0x3bcc3be9,0xb328b0cb,0x396b39d8,0xb9e3b976,
0x3b713ba4,0xb5dfb4bd,0x387a38f6,0xbaa2ba47,0x3aeb3b33,0xb805b6f9,0x36dd37ee,0xbb3abaf3,0x3bf93c00,0xad330000,0x39f43a5e,0xb958b8d8,
0x3bc33be5,0xb3bab12e,0x39023980,0xba3db9d0,0x3b593b95,0xb654b51d,0x37dd387c,0xbaf7baa0,0x3abd3b11,0xb850b780,0x358136b5,0xbb83bb43,
0x3bf83c00,0xad970000,0x39a63a1f,0xb9aab927,0x3bba3be1,0xb426b191,0x38943922,0xba90ba23,0x3b3f3b84,0xb6c6b57c,0x36bb37f9,0xbb42baf0,
0x3a8c3aed,0xb899b802,0x341a3570,0xbbbcbb86,0x3bf73c00,0xadfb0000,0x395439dc,0xb9f8b972,0x3bb03bdc,0xb46fb1f4,0x382038bf,0xbadbba71,
0x3b243b72,0xb737b5da,0x358d36ee,0xbb81bb36,0x3a583ac6,0xb8e0b842,0x31533420,0xbbe3bbbb,0x3bf63c00,0xae5f0000,0x38fd3996,0xba41b9ba,
0x3ba53bd7,0xb4b7b257,0x374e3858,0xbb1ebab8,0x3b073b5f,0xb7a6b637,0x345735da,0xbbb3bb72,0x3a213a9c,0xb924b881,0x2cce3191,0xbbfabbe1,
0x3bf53c00,0xaec30000,0x38a3394d,0xba85b9fe,0x3b9a3bd2,0xb4ffb2b9,0x365437d8,0xbb59baf9,0x3ae83b4b,0xb80ab693,0x323234bd,0xbbd9bba4,
0x39e73a71,0xb966b8bf,0xa4522db0,0xbc00bbf8,0x3bf33c00,0xaf270000,0x38453900,0xbac4ba3f,0x3b8e3bcd,0xb546b31b,0x355236f9,0xbb8bbb33,
0x3ac73b36,0xb840b6ee,0x2f593334,0xbbf2bbcb,0x39aa3a43,0xb9a6b8fb,0xaef51a48,0xbbf4bc00,0x3bf23c00,0xaf8b0000,0x37c838b0,0xbafeba7c,
0x3b813bc7,0xb58db37d,0x344b3614,0xbbb5bb67,0x3aa53b20,0xb874b748,0x288430e4,0xbbffbbe8,0x396b3a13,0xb9e3b935,0xb263ad4c,0xbbd7bbf9,
0x3bf03c00,0xafef0000,0x36ff385d,0xbb32bab5,0x3b733bc1,0xb5d4b3df,0x327c3529,0xbbd6bb93,0x3a813b08,0xb8a8b7a1,0xa9b12d1a,0xbbfebbf9,
0x392939e1,0xba1db96d,0xb49fb160,0xbba9bbe3,0x3bef3c00,0xb0290000,0x36313807,0xbb60bae9,0x3b653bbb,0xb61ab420,0x305b3438,0xbbedbbb7,
0x3a5c3af0,0xb8dbb7f9,0xafef1e48,0xbbf0bc00,0x38e539ad,0xba54b9a4,0xb602b408,0xbb6abbbe,0x3bed3c00,0xb05b0000,0x355e375e,0xbb89bb1a,
0x3b573bb4,0xb65fb451,0x2c6a3288,0xbbfbbbd5,0x3a353ad6,0xb90cb828,0xb27cac51,0xbbd6bbfb,0x389e3976,0xba89b9d8,0xb759b558,0xbb1bbb8a,
0x3beb3c00,0xb08d0000,0x348736aa,0xbbacbb46,0x3b473bad,0xb6a4b481,0x16483099,0xbc00bbeb,0x3a0d3abc,0xb93cb852,0xb47bb080,0xbbaebbec,
0x3855393e,0xbababa0b,0xb850b69e,0xbabdbb49,0x3be93c00,0xb0be0000,0x335935f1,0xbbc9bb6e,0x3b373ba6,0xb6e8b4b1,0xac382d4c,0xbbfcbbf9,
0x39e33aa0,0xb96bb87c,0xb5b1b2d2,0xbb7abbd1,0x380a3905,0xbae8ba3b,0xb8eab7d8,0xba50baf9,0x3be73c00,0xb0f00000,0x319e3534,0xbbe0bb91,
0x3b273b9e,0xb72cb4e1,0xb042257f,0xbbeebc00,0x39b83a83,0xb999b8a6,0xb6ddb48d,0xbb3abbab,0x377a38c9,0xbb13ba69,0xb979b881,0xb9d6ba9c,
0x3be53c00,0xb1220000,0x2fbd3475,0xbbf1bbaf,0x3b163b97,0xb76fb511,0xb263a91b,0xbbd7bbfe,0x398b3a65,0xb9c5b8ce,0xb7feb5ab,0xbaeebb7b,
0x36dd388c,0xbb3aba95,0xb9fcb90e,0xb94fba33,0x3be33c00,0xb1530000,0x2c383365,0xbbfcbbc9,0x3b043b8f,0xb7b2b540,0xb43eae78,0xbbb7bbf6,
0x395d3a47,0xb9f0b8f6,0xb889b6c1,0xba97bb41,0x363c384d,0xbb5ebabf,0xba73b992,0xb8bcb9be,0x3be13c00,0xb1850000,0x217f31db,0xbc00bbdd,
0x3af13b86,0xb7f3b570,0xb546b12e,0xbb8ebbe5,0x392e3a27,0xba19b91d,0xb90cb7cd,0xba35bafc,0x3599380d,0xbb7fbae6,0xbadbba0b,0xb820b93e,
0x3bdf3c00,0xb1b60000,0xa9b1304e,0xbbfebbed,0x3ade3b7d,0xb81ab59f,0xb648b31b,0xbb5cbbcd,0x38fd3a07,0xba41b943,0xb986b867,0xb9c9baae,
0x34f33796,0xbb9cbb0b,0xbb35ba78,0xb6f4b8b5,0x3bdd3c00,0xb1e80000,0xae5f2d7e,0xbbf6bbf8,0x3acb3b74,0xb83ab5ce,0xb742b481,0xbb21bbad,
0x38cc39e5,0xba67b969,0xb9f8b8e2,0xb954ba56,0x344b3710,0xbbb5bb2e,0xbb7fbad9,0xb599b822,0x3bda3c00,0xb2190000,0xb0f028b6,0xbbe7bbff,
0x3ab63b6b,0xb85ab5fd,0xb81ab570,0xbadebb86,0x389939c3,0xba8cb98d,0xba60b956,0xb8d6b9f6,0x33403687,0xbbcbbb4e,0xbbb8bb2e,0xb432b710,
0x3bff3bff,0xa6ada648,0x3bfe3bff,0xa8e8a8b6,0x3bff3bff,0xa776a711,0x3bfe3bfe,0xa94da91b,0x3bff3bff,0xa81fa7da,0x3bfe3bfe,0xa9b1a97f,
0x3bff3bff,0xa884a852,0x3bfe3bfe,0xaa16a9e3,0x3bef3bf1,0xb029afd6,0x3bda3bdd,0xb219b1db,0x3bea3bed,0xb0a6b067,0x3bd43bd7,0xb294b257,
0x3be53be8,0xb122b0e4,0x3bce3bd1,0xb30fb2d2,0x3be03be3,0xb19eb160,0x3bc63bca,0xb389b34c,0x3bc83bce,0xb371b303,0x3b873b91,0xb56ab534,
0x3bba3bc1,0xb426b3df,0x3b733b7d,0xb5d4b59f,0x3bab3bb2,0xb493b45d,0x3b5e3b69,0xb63cb608,0x3b9a3ba2,0xb4ffb4c9,0x3b473b53,0xb6a4b670,
0x3b8b3b99,0xb552b505,0x3b073b1a,0xb7a6b75e,0x3b6f3b7d,0xb5ebb59f,0x3ade3af3,0xb81ab7ee,0x3b4f3b5f,0xb682b637,0x3ab33ac9,0xb85fb83d,
0x3b2c3b3e,0xb715b6cc,0x3a853a9c,0xb8a3b881,0x3b3a3b50,0xb6ddb67c,0x3a5c3a7c,0xb8dbb8b0,0x3b0a3b22,0xb79bb73d,0x3a193a3b,0xb92eb905,
0x3ad53af0,0xb82ab7f9,0x39d239f6,0xb97db956,0x3a9b3ab8,0xb884b858,0x398639ad,0xb9c9b9a4,0x3ad53af6,0xb82ab7e3,0x398b39ba,0xb9c5b996,
0x3a8c3ab1,0xb899b862,0x3929395b,0xba1db9f2,0x3a3d3a65,0xb902b8ce,0x38c138f6,0xba6fba47,0x39e73a13,0xb966b935,0x3855388c,0xbababa95,
0x3a5c3a8a,0xb8dbb89b,0x389938d8,0xba8cba5e,0x39f83a2b,0xb954b918,0x38153858,0xbae1bab8,0x398b39c3,0xb9c5b98d,0x371537a1,0xbb2cbb08,
0x39163951,0xba2db9fa,0x35f73687,0xbb6cbb4e,0x39d23a0f,0xb97db93a,0x371537b7,0xbb2cbb02,0x394f3992,0xb9fcb9be,0x35c83670,0xbb76bb53,
0x38c13909,0xba6fba37,0x346f351d,0xbbb0bb95,0x382a3877,0xbad5baa3,0x3219337d,0xbbdabbc7,0x39373984,0xba11b9cb,0x34cf3593,0xbba1bb80,
0x389438e7,0xba90ba52,0x327c3408,0xbbd6bbbe,0x37c8383d,0xbafebac9,0x2e9130e4,0xbbf5bbe8,0x36543710,0xbb59bb2e,0x16482aac,0xbc00bbfd,
0x388e38ec,0xba93ba4f,0x30d732a1,0xbbe8bbd4,0x3790382d,0xbb0dbad3,0x28e82e14,0xbbfebbf7,0x35eb36c1,0xbb6fbb41,0xaccea4b6,0xbbfabc00,
0x34323511,0xbbb8bb97,0xb201b036,0xbbdcbbee,0x37b23848,0xbb04bac2,0x96482bd9,0xbc00bbfc,0x35df36cc,0xbb71bb3e,0xb010ac1f,0xbbefbbfc,
0x33eb34ed,0xbbc0bb9d,0xb402b20d,0xbbbfbbdb,0x2fef31f4,0xbbf0bbdc,0xb5ebb4f9,0xbb6fbb9b,0x36313732,0xbb60bb25,0xb0f0ad7e,0xbbe7bbf8,
0x341a3529,0xbbbcbb93,0xb49fb31b,0xbba9bbcd,0x2fbd320d,0xbbf1bbdb,0xb6afb5ab,0xbb45bb7b,0xa4522aac,0xbc00bbfd,0xb850b7ac,0xbabdbb05,
0x349f35c2,0xbba9bb77,0xb4dbb365,0xbb9fbbc9,0x308d32ea,0xbbebbbd0,0xb715b5fd,0xbb2cbb6b,0x9fdb2c51,0xbc00bbfb,0xb894b812,0xba90bae3,
0xb109ad4c,0xbbe6bbf9,0xb982b90e,0xb9cdba33,0x32013444,0xbbdcbbb6,0xb721b5f1,0xbb2abb6e,0x26ad2edc,0xbbffbbf4,0xb8adb822,0xba7ebad9,
0xb05bab11,0xbbedbbfd,0xb9aab930,0xb9a6ba17,0xb4b7b2ea,0xbba5bbd0,0xba81ba1b,0xb8a8b92b,0x2d653179,0xbbf9bbe2,0xb89eb807,0xba89bae9,
0xadc99a48,0xbbf8bc00,0xb9afb92b,0xb9a1ba1b,0xb432b1aa,0xbbb8bbe0,0xba93ba27,0xb88eb91d,0xb6d2b587,0xbb3dbb82,0xbb45baf3,0xb6afb7ee,
0xa51b2cb5,0xbc00bbfa,0xb990b900,0xb9c0ba3f,0xb294af40,0xbbd4bbf3,0xba89ba13,0xb89eb935,0xb625b4bd,0xbb63bba4,0xbb47baf0,0xb6a4b7f9,
0xb865b780,0xbab0bb11,0xbbc5bb8f,0xb3a2b540,0xafefa648,0xbbf0bbff,0xba60b9dc,0xb8d6b972,0xb517b31b,0xbb96bbcd,0xbb35bad3,0xb6f4b82d,
0xb7feb693,0xbaeebb4b,0xbbc0bb84,0xb3ebb57c,0xb94ab8ab,0xba00ba7f,0xbbfdbbe9,0xaa7ab0cb,0xb340afd6,0xbbcbbbf1,0xbb0aba99,0xb79bb887,
0xb6d2b540,0xbb3dbb8f,0xbbaebb67,0xb47bb614,0xb8dbb828,0xba5cbad6,0xbbfbbbe0,0xac9cb1aa,0xba15b980,0xb933b9d0,0xbbecbbff,0x30742852,
0xb53ab303,0xbb90bbce,0xbb89bb30,0xb55eb705,0xb83ab6e3,0xbacbbb39,0xbbf2bbca,0xaf8bb34c,0xb9a1b8f6,0xb9afba47,0xbbf5bc00,0x2ec39e48,
0xbac1ba3b,0xb84ab905,0xbb92bbd0,0x352f32ea,0xb6c6b505,0xbb3fbb99,0xbbdcbba0,0xb201b4d5,0xb8fdb838,0xba41bacc,0xbbfebbfb,0x2a16ac83,
0xba50b9b1,0xb8eab99f,0xbbaebbe4,0x347b3147,0xbb4abad9,0xb699b822,0xbaf1bb5d,0x37f33642,0xb820b67c,0xbadbbb50,0xbbffbbe6,0xa884b115,
0xb9afb8f1,0xb9a1ba4b,0xbbd2bbf8,0x32c62db0,0xbae5ba56,0xb80fb8e2,0xbb2abb8c,0x3721354c,0xbbaebb58,0xb47bb659,0xba11baaa,0x3937386d,
0xb8d1b7e3,0xba64baf6,0xbbf2bc00,0x2f8ba248,0xba4db99b,0xb8eeb9b5,0xbb6fbbc1,0x35eb33df,0xbb5cbae3,0xb648b812,0xba6bbafc,0x38c737cd,
0xbbebbbb4,0xb08db451,0xb8f8b9be,0x3a453992,0xb974b89b,0xb9daba8a,0xbbb5bbed,0x344b304e,0xbad5ba33,0xb82ab90e,0xbad8bb58,0x38253659,
0xbbb3bb55,0xb457b665,0xb979ba37,0x39d63909,0xbc00bbed,0x9648b067,0xb764b8a0,0x3b183a87,0xba09b93a,0xb941ba0f,0xbb4abbaf,0x36993475,
0xbb45bab8,0xb6afb858,0xba11babf,0x3937384d,0xbbeabbab,0xb0a6b48d,0xb85ab943,0x3ab63a07,0xbbecbc00,0x30749a48,0xb493b6b5,0x3bab3b43,
0xba8cb9cb,0xb899b984,0xbab3bb46,0x385f36aa,0xbb9cbb28,0xb4f3b726,0xb91fb9fa,0x3a253951,0xbc00bbe4,0xa452b147,0xb631b828,0x3b603ad6,
0xbbb0bbee,0x346f3036,0xae5fb3df,0x3bf63bc1,0xbafeba4f,0xb7c8b8ec,0xb9f4bab5,0x3958385d,0xbbd8bb82,0xb24bb587,0xb80ab90e,0x3ae83a33,
0xbbf3bbfe,0x2f27a97f,0xb2f7b5da,0x3bcf3b72,0xbb4cbbb7,0x368d3438,0x2dc9ac1f,0x3bf83bfc,0xbb5cbac2,0xb648b848,0xb911b9fe,0x3a31394d,
0xbbf9bbc4,0xad33b3ae,0xb5b1b802,0x3b7a3aed,0xbbc5bbf9,0x33a22d1a,0xa94db26f,0x3bfe3bd6,0xbac4bb5d,0x38453642,0x346f2fa4,0x3bb03bf1,
0xbba5bb25,0xb4b7b732,0xb80fb927,0x3ae53a1f,0xbbffbbee,0x2884b036,0xb24bb5b6,0x3bd83b79,0xbb76bbd6,0x35c8326f,0x305ba7da,0x3bed3bff,
0xba19bae0,0x392e3817,0x374234c9,0x3b213ba2,0xbbd9bb77,0xb232b5c2,0xb5ebb832,0x3b6f3ad0,0xbbe8bc00,0x30d7a57f,0xa81fb288,0x3bff3bd5,
0xbb07bb95,0x37a6351d,0x34f33080,0x3b9c3bec,0xb94fba43,0x39fc38fb,0x38ea3780,0x3a503b11,0xbbf8bbb6,0xadc9b444,0xb328b64e,0x3bcc3b5a,
0xbbb7bbf8,0x343e2db0,0x3042a9e3,0x3bee3bfe,0xba7abb36,0x38b236ee,0x379034ed,0x3b0d3b9d,0xb86ab989,0x3aac39c7,0x3a0438fb,0x39463a43,
0xbc00bbe2,0x2311b179,0xac9cb414,0x3bfb3bbc,0xbb6abbd7,0x36023257,0x34b72f40,0x3ba53bf3,0xb9d2babc,0x397d3852,0x38f83775,0x3a453b14,
0xb6ddb8b5,0x3b3a3a78,0x3ae83a0b,0x380a393e,0xbbf2bbfa,0x2f8bacb5,0x2d33af0e,0x3bf93bf4,0xbb04bb9e,0x37b234e1,0x372c3451,0x3b273bb4,
0xb911ba27,0x3a31391d,0x3a0038e2,0x394a3a56,0xb4c3b796,0x3ba33b0b,0x3b8b3ae6,0x3552380d,0x4c004c00,0x26480000,0x4c004c00,0x33113248,
0x4c004c00,0x2cb62a48,0x4c004c00,0x345233db,0x4c004c00,0x2fdb2e48,0x4c004c00,0x351b34b6,0x4c004c00,0x317f30b6,0x4bff4c00,0x35e4357f,
0x4c004c00,0x2fdb0000,0x4bfb4bfc,0x3c6a3bd9,0x4bff4c00,0x35e433db,0x4bf94bfa,0x3d653ce7,0x4bfe4bff,0x38e837da,0x4bf64bf7,0x3e5f3de2,
0x4bfd4bfe,0x3ade39e3,0x4bf24bf4,0x3f593edc,0x4c004c00,0x33110000,0x4bf04bf4,0x3fef3f0e,0x4bfe4bff,0x394d3711,0x4be84bed,0x40d74067,
0x4bfb4bfd,0x3c6a3b11,0x4bdf4be4,0x41b64147,0x4bf64bf9,0x3e2d3d4c,0x4bd44bda,0x42944226,0x4c004c00,0x351b0000,0x4bdf4be6,0x41b64115,
0x4bfc4bfe,0x3ba7391b,0x4bcf4bd7,0x42f74257,0x4bf64bf9,0x3e5f3d1a,0x4bbc4bc6,0x441a4396,0x4bec4bf1,0x40743fa4,0x4ba54bb1,0x44b74469,
0x4bff4c00,0x36ad0000,0x4bc84bd4,0x437142a1,0x4bfa4bfd,0x3d003aac,0x4bac4bbb,0x44874420,0x4bef4bf5,0x40293eaa,0x4b8b4b9d,0x455244ed,
0x4bde4be7,0x41cf40fd,0x4b654b79,0x461a45b6,0x4bff4c00,0x381f0000,0x4bab4bbc,0x44934414,0x4bf64bfc,0x3e2d3c1f,0x4b814b97,0x458d4511,
0x4be54bef,0x4122401d,0x4b4f4b69,0x46824608,0x4bcc4bda,0x43284226,0x4b164b33,0x476f46f9,0x4bfe4c00,0x38e80000,0x4b874ba0,0x456a44d5,
0x4bf24bfa,0x3f593ce7,0x4b4c4b6b,0x468d45fd,0x4bda4be8,0x421940e4,0x4b074b2b,0x47a6471b,0x4bb74bca,0x443e434c,0x4ab64ae0,0x485a4817,
0x4bfe4c00,0x39b10000,0x4b5e4b80,0x463c4593,0x4bee4bf8,0x40423db0,0x4b104b39,0x478546e3,0x4bce4be0,0x430f41aa,0x4ab34ae3,0x485f4812,
0x4b9e4bb7,0x44e74438,0x4a494a7f,0x48f348ab,0x4bfd4c00,0x3a7a0000,0x4b2f4b5a,0x470a464e,0x4be84bf6,0x40d73e78,0x4acb4aff,0x483a47c2,
0x4bbf4bd6,0x4402426f,0x4a544a92,0x48e54891,0x4b814ba2,0x458d44c9,0x49cd4a13,0x49824935,0x4bfd4c00,0x3b430000,0x4afb4b30,0x47d24705,
0x4be24bf3,0x416c3f40,0x4a7e4abf,0x48ad484d,0x4bae4bcb,0x447b4334,0x49eb4a37,0x49624909,0x4b604b8a,0x46314558,0x4946499b,0x4a0449b5,
0x4bfc4c00,0x3c060000,0x4ac14b02,0x484a47b7,0x4bdc4bf0,0x42014004,0x4a294a78,0x491b48b5,0x4b9c4bc0,0x44f343f7,0x497949d4,0x49d6497b,
0x4b3d4b70,0x46d245e5,0x48b24918,0x4a7a4a2b,0x4bfb4c00,0x3c6a0000,0x4a814ad0,0x48a84832,0x4bd44bed,0x42944067,0x49cd4a2b,0x49824918,
0x4b874bb2,0x456a445d,0x48fd4969,0x4a4149e5,0x4b164b53,0x476f4670,0x4815488c,0x4ae14a95,0x4bfa4c00,0x3cce0000,0x4a3d4a99,0x49024887,
0x4bcc4be9,0x432840cb,0x496b49d8,0x49e34976,0x4b714ba4,0x45df44bd,0x487a48f6,0x4aa24a47,0x4aeb4b33,0x480546f9,0x46dd47ee,0x4b3a4af3,
0x4bf94c00,0x3d330000,0x49f44a5e,0x495848d8,0x4bc34be5,0x43ba412e,0x49024980,0x4a3d49d0,0x4b594b95,0x4654451d,0x47dd487c,0x4af74aa0,
0x4abd4b11,0x48504780,0x458146b5,0x4b834b43,0x4bf84c00,0x3d970000,0x49a64a1f,0x49aa4927,0x4bba4be1,0x44264191,0x48944922,0x4a904a23,
0x4b3f4b84,0x46c6457c,0x46bb47f9,0x4b424af0,0x4a8c4aed,0x48994802,0x441a4570,0x4bbc4b86,0x4bf74c00,0x3dfb0000,0x495449dc,0x49f84972,
0x4bb04bdc,0x446f41f4,0x482048bf,0x4adb4a71,0x4b244b72,0x473745da,0x458d46ee,0x4b814b36,0x4a584ac6,0x48e04842,0x41534420,0x4be34bbb,
0x4bf64c00,0x3e5f0000,0x48fd4996,0x4a4149ba,0x4ba54bd7,0x44b74257,0x474e4858,0x4b1e4ab8,0x4b074b5f,0x47a64637,0x445745da,0x4bb34b72,
0x4a214a9c,0x49244881,0x3cce4191,0x4bfa4be1,0x4bf54c00,0x3ec30000,0x48a3494d,0x4a8549fe,0x4b9a4bd2,0x44ff42b9,0x465447d8,0x4b594af9,
0x4ae84b4b,0x480a4693,0x423244bd,0x4bd94ba4,0x49e74a71,0x496648bf,0xb4523db0,0x4c004bf8,0x4bf34c00,0x3f270000,0x48454900,0x4ac44a3f,
0x4b8e4bcd,0x4546431b,0x455246f9,0x4b8b4b33,0x4ac74b36,0x484046ee,0x3f594334,0x4bf24bcb,0x49aa4a43,0x49a648fb,0xbef52a48,0x4bf44c00,
0x4bf24c00,0x3f8b0000,0x47c848b0,0x4afe4a7c,0x4b814bc7,0x458d437d,0x444b4614,0x4bb54b67,0x4aa54b20,0x48744748,0x388440e4,0x4bff4be8,
0x496b4a13,0x49e34935,0xc263bd4c,0x4bd74bf9,0x4bf04c00,0x3fef0000,0x46ff485d,0x4b324ab5,0x4b734bc1,0x45d443df,0x427c4529,0x4bd64b93,
0x4a814b08,0x48a847a1,0xb9b13d1a,0x4bfe4bf9,0x492949e1,0x4a1d496d,0xc49fc160,0x4ba94be3,0x4bef4c00,0x40290000,0x46314807,0x4b604ae9,
0x4b654bbb,0x461a4420,0x405b4438,0x4bed4bb7,0x4a5c4af0,0x48db47f9,0xbfef2e48,0x4bf04c00,0x48e549ad,0x4a5449a4,0xc602c408,0x4b6a4bbe,
0x4bed4c00,0x405b0000,0x455e475e,0x4b894b1a,0x4b574bb4,0x465f4451,0x3c6a4288,0x4bfb4bd5,0x4a354ad6,0x490c4828,0xc27cbc51,0x4bd64bfb,
0x489e4976,0x4a8949d8,0xc759c558,0x4b1b4b8a,0x4beb4c00,0x408d0000,0x448746aa,0x4bac4b46,0x4b474bad,0x46a44481,0x26484099,0x4c004beb,
0x4a0d4abc,0x493c4852,0xc47bc080,0x4bae4bec,0x4855493e,0x4aba4a0b,0xc850c69e,0x4abd4b49,0x4be94c00,0x40be0000,0x435945f1,0x4bc94b6e,
0x4b374ba6,0x46e844b1,0xbc383d4c,0x4bfc4bf9,0x49e34aa0,0x496b487c,0xc5b1c2d2,0x4b7a4bd1,0x480a4905,0x4ae84a3b,0xc8eac7d8,0x4a504af9,
0x4be74c00,0x40f00000,0x419e4534,0x4be04b91,0x4b274b9e,0x472c44e1,0xc042357f,0x4bee4c00,0x49b84a83,0x499948a6,0xc6ddc48d,0x4b3a4bab,
0x477a48c9,0x4b134a69,0xc979c881,0x49d64a9c,0x4be54c00,0x41220000,0x3fbd4475,0x4bf14baf,0x4b164b97,0x476f4511,0xc263b91b,0x4bd74bfe,
0x498b4a65,0x49c548ce,0xc7fec5ab,0x4aee4b7b,0x46dd488c,0x4b3a4a95,0xc9fcc90e,0x494f4a33,0x4be34c00,0x41530000,0x3c384365,0x4bfc4bc9,
0x4b044b8f,0x47b24540,0xc43ebe78,0x4bb74bf6,0x495d4a47,0x49f048f6,0xc889c6c1,0x4a974b41,0x463c484d,0x4b5e4abf,0xca73c992,0x48bc49be,
0x4be14c00,0x41850000,0x317f41db,0x4c004bdd,0x4af14b86,0x47f34570,0xc546c12e,0x4b8e4be5,0x492e4a27,0x4a19491d,0xc90cc7cd,0x4a354afc,
0x4599480d,0x4b7f4ae6,0xcadbca0b,0x4820493e,0x4bdf4c00,0x41b60000,0xb9b1404e,0x4bfe4bed,0x4ade4b7d,0x481a459f,0xc648c31b,0x4b5c4bcd,
0x48fd4a07,0x4a414943,0xc986c867,0x49c94aae,0x44f34796,0x4b9c4b0b,0xcb35ca78,0x46f448b5,0x4bdd4c00,0x41e80000,0xbe5f3d7e,0x4bf64bf8,
0x4acb4b74,0x483a45ce,0xc742c481,0x4b214bad,0x48cc49e5,0x4a674969,0xc9f8c8e2,0x49544a56,0x444b4710,0x4bb54b2e,0xcb7fcad9,0x45994822,
0x4bda4c00,0x42190000,0xc0f038b6,0x4be74bff,0x4ab64b6b,0x485a45fd,0xc81ac570,0x4ade4b86,0x489949c3,0x4a8c498d,0xca60c956,0x48d649f6,
0x43404687,0x4bcb4b4e,0xcbb8cb2e,0x44324710,0x4bd84c00,0x424b0000,0xc2adb248,0x4bd34c00,0x4aa24b62,0x487a462b,0xc88ec659,0x4a934b58,
0x4865499f,0x4ab049b1,0xcabdc9c3,0x4850498d,0x41e845fd,0x4bdd4b6b,0xcbe1cb74,0x418545ce,0x4bd64c00,0x427c0000,0xc432bbd9,0x4bb84bfc,
0x4a8c4b58,0x48994659,0xc8fdc73d,0x4a414b22,0x4830497b,0x4ad149d4,0xcb10ca27,0x4785491d,0x408d4570,0x4beb4b86,0xcbf9cbad,0x3d334481,
0x4bd34c00,0x42ad0000,0xc50bbf0e,0x4b984bf4,0x4a764b4e,0x48b74687,0xc966c80d,0x49e74ae6,0x47f34956,0x4af149f6,0xcb57ca83,0x465f48a6,
0x3e5f44e1,0x4bf64b9e,0xcc00cbd7,0xb17f4257,0x4bd04c00,0x42de0000,0xc5dfc115,0x4b714be6,0x4a604b43,0x48d646b5,0xc9c9c877,0x49864aa3,
0x47854930,0x4b104a17,0xcb92cad6,0x452f4828,0x3b434451,0x4bfd4bb4,0xcbf5cbf3,0xbe913f40,0x4bce4c00,0x430f0000,0xc6afc2a1,0x4b454bd4,
0x4a494b39,0x48f346e3,0xca25c8dd,0x491f4a5a,0x47154909,0x4b2c4a37,0xcbc0cb20,0x43eb4748,0x3311437d,0x4c004bc7,0xcbd9cbff,0xc2323711,
0x4bcb4c00,0x43400000,0xc77ac414,0x4b134bbc,0x4a314b2e,0x49114710,0xca7ac93e,0x48b24a0b,0x46a448e2,0x4b474a56,0xcbe2cb5f,0x416c4637,
0xb7764257,0x4bff4bd7,0xcbaccbfd,0xc487bb75,0x4bc84c00,0x43710000,0xc820c4d5,0x4adb4ba0,0x4a194b22,0x492e473d,0xcac7c99b,0x484049b5,
0x463148ba,0x4b604a74,0xcbf8cb95,0x3dc9451d,0xbc9c412e,0x4bfb4be5,0xcb6fcbeb,0xc5ebc099,0x4bc54c00,0x43a20000,0xc87fc593,0x4a9e4b80,
0x4a004b17,0x494a476a,0xcb0dc9f2,0x4790495b,0x45bc4891,0x4b784a92,0xcc00cbc0,0x317f43f7,0xbf594004,0x4bf24bf0,0xcb21cbca,0xc742c34c,
0x4bc24c00,0x43d30000,0xc8dbc64e,0x4a5c4b5a,0x49e74b0b,0x49664796,0xcb4aca43,0x469948fb,0x45464867,0x4b8e4aae,0xcbfbcbe0,0xbc6a41aa,
0xc1093db0,0x4be64bf8,0xcac4cb9b,0xc845c4f9,0x4bbf4c00,0x44020000,0xc933c705,0x4a154b30,0x49cd4aff,0x498247c2,0xcb7fca8e,0x45994896,
0x44cf483d,0x4ba14ac9,0xcbe9cbf5,0xc0be3eaa,0xc2633aac,0x4bd74bfd,0xca58cb5d,0xc8e0c642,0x4bbc4c00,0x441a0000,0xc986c7b7,0x49c94b02,
0x49b34af3,0x499d47ee,0xcbabcad3,0x4493482d,0x44574812,0x4bb34ae3,0xcbcbcbff,0xc34037da,0xc3ba33db,0x4bc34c00,0xc9dfcb11,0xc970c780,
0x4bb84c00,0x44320000,0xc9d6c832,0x49794ad0,0x49994ae6,0x49b8480d,0xcbcecb11,0x430f4780,0x43ba47cd,0x4bc34afc,0xcb9fcbfe,0xc4dbb97f,
0xc487b57f,0x4bac4c00,0xc958cab8,0xc9f4c858,0x4bb54c00,0x444b0000,0xca21c887,0x49244a99,0x497d4ad9,0x49d24822,0xcbe7cb49,0x40f0469e,
0x42c64775,0x4bd24b14,0xcb68cbf2,0xc60ebf72,0xc52fbb75,0x4b924bfd,0xc8c7ca52,0xca6bc8e7,0x4bb24c00,0x44630000,0xca67c8d8,0x48cc4a5e,
0x49624acc,0x49eb4838,0xcbf8cb79,0x3d9745b6,0x41cf471b,0x4bde4b2b,0xcb24cbdb,0xc737c20d,0xc5d4be14,0x4b734bf7,0xc82ac9e1,0xcad5c96d,
0x4bae4c00,0x447b0000,0xcaa9c927,0x486f4a1f,0x49464abf,0x4a04484d,0xcc00cba2,0x351b44c9,0x40d746c1,0x4be84b41,0xcad5cbb9,0xc82ac42c,
0xc676c036,0x4b524bee,0xc70ac964,0xcb2fc9e9,0x4bab4c00,0x44930000,0xcae5c972,0x480f49dc,0x49294ab1,0x4a1d4862,0xcbfecbc4,0xba1643ae,
0x3fbd4665,0x4bf14b55,0xca7acb8c,0xc8b2c54c,0xc715c160,0x4b2c4be3,0xc5b1c8dd,0xcb7aca5a,0x4ba74c00,0x44ab0000,0xcb1bc9ba,0x47594996,
0x490c4aa3,0x4a354877,0xcbf2cbdf,0xbf5941c3,0x3dc94608,0x4bf84b69,0xca15cb55,0xc933c665,0xc7b2c288,0x4b044bd5,0xc44bc84d,0xcbb5cabf,
0x4ba34c00,0x44c30000,0xcb4cc9fe,0x468d494d,0x48ee4a95,0x4a4d488c,0xcbdecbf1,0xc1cf3fa4,0x3ba745ab,0x4bfc4b7b,0xc9a6cb14,0xc9aac775,
0xc825c3ae,0x4ad84bc4,0xc1b6c76a,0xcbdfcb17,0x4b9f4c00,0x44db0000,0xcb78ca3f,0x45bc4900,0x48d14a87,0x4a6448a0,0xcbc0cbfd,0xc3eb3b75,
0x3776454c,0x4bff4b8c,0xc92ecac9,0xca19c83d,0xc86fc469,0x4aa94bb1,0xbd97c62b,0xcbf8cb62,0x4b9c4c00,0x44f30000,0xcb9eca7c,0x44e748b0,
0x48b24a78,0x4a7a48b5,0xcb9acc00,0xc4ffaa48,0xa64844ed,0x4c004b9d,0xc8adca74,0xca7ec8ba,0xc8b7c4f9,0x4a764b9b,0x2cb6c4e1,0xcc00cb9e,
0x4b984c00,0x450b0000,0xcbbdcab5,0x440e485d,0x48944a69,0x4a9048c9,0xcb6acbfc,0xc602bc1f,0xb81f448d,0x4bff4bab,0xc825ca17,0xcad8c930,
0xc8fdc587,0x4a414b82,0x3e2dc31b,0xcbf6cbcd,0x4b944c00,0x45230000,0xcbd7cae9,0x42634807,0x48744a5a,0x4aa548dd,0xcb32cbf0,0xc6ffc004,
0xbc06442c,0x4bfc4bb9,0xc72cc9b1,0xcb27c99f,0xc941c614,0x4a094b67,0x4201c067,0xcbdccbed,0x4b904c00,0x453a0000,0xcbeacb1a,0x40a6475e,
0x48554a4b,0x4aba48f1,0xcaf1cbdc,0xc7f3c1f4,0xbdfb4396,0x4bf74bc6,0xc602c943,0xcb6aca07,0xc982c69e,0x49cd4b49,0x446fbaac,0xcbb0cbfd,
0x4b8b4c00,0x45520000,0xcbf8cb46,0x3dc946aa,0x48354a3b,0x4ace4905,0xcaa9cbc1,0xc86fc3df,0xbfef42d2,0x4bf04bd1,0xc4cfc8ce,0xcba1ca65,
0xc9c0c726,0x49904b28,0x45d43852,0xcb73cbff,0x4b874c00,0x456a0000,0xcbffcb6e,0x388445f1,0x48154a2b,0x4ae14918,0xca58cb9e,0xc8e0c4e1,
0xc0f0420d,0x4be74bdb,0xc328c852,0xcbcccabc,0xc9fcc7ac,0x494f4b05,0x472c3fa4,0xcb27cbf1,0x4b834c00,0x45810000,0xcc00cb91,0xb51b4534,
0x47e84a1b,0x4af4492b,0xca00cb74,0xc94ac5ce,0xc1e84147,0x4bdd4be4,0xc0a6c7a1,0xcbeacb08,0xca35c817,0x490c4ae0,0x483a4288,0xcacbcbd5,
0x4b7f4c00,0x45990000,0xcbfacbaf,0xbcce4475,0x47a64a0b,0x4b07493e,0xc9a1cb43,0xc9afc6b5,0xc2de4080,0x4bd04bec,0xbc38c693,0xcbfccb4b,
0xca6bc858,0x48c74ab8,0x48d64499,0xca60cbaa,0x4b7a4c00,0x45b10000,0xcbefcbc9,0xc0294365,0x476449fa,0x4b184951,0xc93ccb0b,0xca0dc796,
0xc3d33f72,0x4bc24bf2,0x3311c57c,0xcc00cb84,0xca9ec896,0x487f4a8e,0x496645e5,0xc9e7cb70,0x4b764c00,0x45c80000,0xcbddcbdd,0xc1e841db,
0x472149e9,0x4b2a4964,0xc8d1cacc,0xca64c838,0xc4633de2,0x4bb24bf7,0x3dfbc45d,0xcbf7cbb2,0xcacec8d3,0x48354a62,0x49eb4726,0xc962cb28,
0x4b714c00,0x45df0000,0xcbc5cbed,0xc3a2404e,0x46dd49d8,0x4b3a4976,0xc85fca87,0xcab3c8a0,0xc4db3c51,0x4b9f4bfb,0x4185c26f,0xcbe1cbd6,
0xcafbc90e,0x47d24a33,0x4a64482d,0xc8d1cad3,0x4b6c4c00,0x45f70000,0xcba7cbf8,0xc4ab3d7e,0x469949c7,0x4b4a4989,0xc7d2ca3b,0xcafbc905,
0xc552397f,0x4b8b4bfe,0x4402c01d,0xcbbfcbef,0xcb24c948,0x47374a02,0x4ace48bf,0xc835ca71,0x4b684c00,0x460e0000,0xcb83cbff,0xc58138b6,
0x465449b5,0x4b59499b,0xc6ddc9e9,0xcb3ac964,0xc5c834b6,0x4b764c00,0x453abb11,0xcb90cbfd,0xcb4ac980,0x469949d0,0x4b2a4948,0xc721ca02,
0x2c002c00,0x2c002c00,0x2c002c00,0x2c002c00,0x2b642c00,0x261f29a8,0xa61f0000,0xab64a9a8,0x29a82c00,0xa9a80000,0xa9a8ac00,0x29a80000,
0x261f2c00,0xab64a9a8,0x2b640000,0xa61f29a8,0x2c00,0xac00,0x2c00,0xac00,0xa61f2c00,0x2b64a9a8,0xab640000,0x261f29a8,
0xa9a82c00,0x29a80000,0x29a8ac00,0xa9a80000,0xab642c00,0xa61f29a8,0x261f0000,0x2b64a9a8,0,0,0,0,
0x261f0000,0x2b6429a8,0x2b642c00,0x261f29a8,0x29a80000,0x29a82c00,0xa9a80000,0xa9a8ac00,0x2b640000,0xa61f29a8,0xa61fac00,0x2b6429a8,
0x2c000000,0xac000000,0x2c000000,0xac000000,0x2b640000,0xa61fa9a8,0xa61f2c00,0x2b64a9a8,0x29a80000,0x29a8ac00,0xa9a80000,0xa9a82c00,
0x261f0000,0x2b64a9a8,0x2b64ac00,0x261fa9a8,0xac002c00,0xac002c00,0xac002c00,0xac002c00,0xab642c00,0xa61f29a8,0x261f0000,0x2b64a9a8,
0xa9a82c00,0x29a80000,0x29a8ac00,0xa9a80000,0xa61f2c00,0x2b64a9a8,0xab640000,0x261f29a8,0x2c00,0xac00,0x2c00,0xac00,
0x261f2c00,0xab64a9a8,0x2b640000,0xa61f29a8,0x29a82c00,0xa9a80000,0xa9a8ac00,0x29a80000,0x2b642c00,0x261f29a8,0xa61f0000,0xab64a9a8,
0,0,0,0,0xa61f0000,0xab6429a8,0xab642c00,0xa61f29a8,0xa9a80000,0xa9a82c00,0x29a80000,0x29a8ac00,
0xab640000,0x261f29a8,0x261fac00,0xab6429a8,0xac000000,0x2c000000,0xac000000,0x2c000000,0xab640000,0x261fa9a8,0x261f2c00,0xab64a9a8,
0xa9a80000,0xa9a8ac00,0x29a80000,0x29a82c00,0xa61f0000,0xab64a9a8,0xab64ac00,0xa61fa9a8,0,0,0,0,
0xa61f0000,0xab64a9a8,0xab64ac00,0xa61fa9a8,0xa9a80000,0xa9a8ac00,0x29a80000,0x29a82c00,0xab640000,0x261fa9a8,0x261f2c00,0xab64a9a8,
0xac000000,0x2c000000,0xac000000,0x2c000000,0xab640000,0x261f29a8,0x261fac00,0xab6429a8,0xa9a80000,0xa9a82c00,0x29a80000,0x29a8ac00,
0xa61f0000,0xab6429a8,0xab642c00,0xa61f29a8,0x2c002c00,0x2c002c00,0x2c002c00,0x2c002c00,0x2b642c00,0x261f29a8,0xa61f0000,0xab64a9a8,
0x29a82c00,0xa9a80000,0xa9a8ac00,0x29a80000,0x261f2c00,0xab64a9a8,0x2b640000,0xa61f29a8,0x2c00,0xac00,0x2c00,0xac00,
0xa61f2c00,0x2b64a9a8,0xab640000,0x261f29a8,0xa9a82c00,0x29a80000,0x29a8ac00,0xa9a80000,0xab642c00,0xa61f29a8,0x261f0000,0x2b64a9a8,
0,0,0,0,0x261f0000,0x2b64a9a8,0x2b64ac00,0x261fa9a8,0x29a80000,0x29a8ac00,0xa9a80000,0xa9a82c00,
0x2b640000,0xa61fa9a8,0xa61f2c00,0x2b64a9a8,0x2c000000,0xac000000,0x2c000000,0xac000000,0x2b640000,0xa61f29a8,0xa61fac00,0x2b6429a8,
0x29a80000,0x29a82c00,0xa9a80000,0xa9a8ac00,0x261f0000,0x2b6429a8,0x2b642c00,0x261f29a8,0xac002c00,0xac002c00,0xac002c00,0xac002c00,
0xab642c00,0xa61f29a8,0x261f0000,0x2b64a9a8,0xa9a82c00,0x29a80000,0x29a8ac00,0xa9a80000,0xa61f2c00,0x2b64a9a8,0xab640000,0x261f29a8,
0x2c00,0xac00,0x2c00,0xac00,0x261f2c00,0xab64a9a8,0x2b640000,0xa61f29a8,0x29a82c00,0xa9a80000,0xa9a8ac00,0x29a80000,
0x2b642c00,0x261f29a8,0xa61f0000,0xab64a9a8,0x2c002c00,0x2c002c00,0x2c002c00,0x2c002c00,0xab64ac00,0xa61fa9a8,0x261f0000,0x2b6429a8,
0x29a82c00,0xa9a80000,0xa9a8ac00,0x29a80000,0xa61fac00,0x2b6429a8,0xab640000,0x261fa9a8,0x2c00,0xac00,0x2c00,0xac00,
0x261fac00,0xab6429a8,0x2b640000,0xa61fa9a8,0xa9a82c00,0x29a80000,0x29a8ac00,0xa9a80000,0x2b64ac00,0x261fa9a8,0xa61f0000,0xab6429a8,
0,0,0,0,0xa61f0000,0xab64a9a8,0xab64ac00,0xa61fa9a8,0x29a80000,0x29a82c00,0xa9a80000,0xa9a8ac00,
0xab640000,0x261fa9a8,0x261f2c00,0xab64a9a8,0x2c000000,0xac000000,0x2c000000,0xac000000,0xab640000,0x261f29a8,0x261fac00,0xab6429a8,
0x29a80000,0x29a8ac00,0xa9a80000,0xa9a82c00,0xa61f0000,0xab6429a8,0xab642c00,0xa61f29a8,0xac002c00,0xac002c00,0xac002c00,0xac002c00,
0x2b64ac00,0x261fa9a8,0xa61f0000,0xab6429a8,0xa9a82c00,0x29a80000,0x29a8ac00,0xa9a80000,0x261fac00,0xab6429a8,0x2b640000,0xa61fa9a8,
0x2c00,0xac00,0x2c00,0xac00,0xa61fac00,0x2b6429a8,0xab640000,0x261fa9a8,0x29a82c00,0xa9a80000,0xa9a8ac00,0x29a80000,
0xab64ac00,0xa61fa9a8,0x261f0000,0x2b6429a8,0,0,0,0,0x261f0000,0x2b64a9a8,0x2b64ac00,0x261fa9a8,
0xa9a80000,0xa9a82c00,0x29a80000,0x29a8ac00,0x2b640000,0xa61fa9a8,0xa61f2c00,0x2b64a9a8,0xac000000,0x2c000000,0xac000000,0x2c000000,
0x2b640000,0xa61f29a8,0xa61fac00,0x2b6429a8,0xa9a80000,0xa9a8ac00,0x29a80000,0x29a82c00,0x261f0000,0x2b6429a8,0x2b642c00,0x261f29a8,
0,0,0,0,0x261f0000,0x2b6429a8,0x2b642c00,0x261f29a8,0xa9a80000,0xa9a8ac00,0x29a80000,0x29a82c00,
0x2b640000,0xa61f29a8,0xa61fac00,0x2b6429a8,0xac000000,0x2c000000,0xac000000,0x2c000000,0x2b640000,0xa61fa9a8,0xa61f2c00,0x2b64a9a8,
0xa9a80000,0xa9a82c00,0x29a80000,0x29a8ac00,0x261f0000,0x2b64a9a8,0x2b64ac00,0x261fa9a8,0x2c002c00,0x2c002c00,0x2c002c00,0x2c002c00,
0xab64ac00,0xa61fa9a8,0x261f0000,0x2b6429a8,0x29a82c00,0xa9a80000,0xa9a8ac00,0x29a80000,0xa61fac00,0x2b6429a8,0xab640000,0x261fa9a8,
0x2c00,0xac00,0x2c00,0xac00,0x261fac00,0xab6429a8,0x2b640000,0xa61fa9a8,0xa9a82c00,0x29a80000,0x29a8ac00,0xa9a80000,
0x2b64ac00,0x261fa9a8,0xa61f0000,0xab6429a8,0,0,0,0,0xa61f0000,0xab6429a8,0xab642c00,0xa61f29a8,
0x29a80000,0x29a8ac00,0xa9a80000,0xa9a82c00,0xab640000,0x261f29a8,0x261fac00,0xab6429a8,0x2c000000,0xac000000,0x2c000000,0xac000000,
0xab640000,0x261fa9a8,0x261f2c00,0xab64a9a8,0x29a80000,0x29a82c00,0xa9a80000,0xa9a8ac00,0xa61f0000,0xab64a9a8,0xab64ac00,0xa61fa9a8,
0xac002c00,0xac002c00,0xac002c00,0xac002c00,0x2b64ac00,0x261fa9a8,0xa61f0000,0xab6429a8,0xa9a82c00,0x29a80000,0x29a8ac00,0xa9a80000,
0x261fac00,0xab6429a8,0x2b640000,0xa61fa9a8,0x2c00,0xac00,0x2c00,0xac00,0xa61fac00,0x2b6429a8,0xab640000,0x261fa9a8,
0x29a82c00,0xa9a80000,0xa9a8ac00,0x29a80000,0xab64ac00,0xa61fa9a8,0x261f0000,0x2b6429a8,0x2bd92c00,0x2aa72b64,0x287229a8,0x223e261f,
0x2aa72c00,0xa23e261f,0xabd9a9a8,0xa872ab64,0x28722c00,0xabd9a61f,0x223ea9a8,0x2aa72b64,0x223e2c00,0xa872ab64,0x2aa729a8,0xabd9a61f,
0xa23e2c00,0x2872ab64,0xaaa729a8,0x2bd9a61f,0xa8722c00,0x2bd9a61f,0xa23ea9a8,0xaaa72b64,0xaaa72c00,0x223e261f,0x2bd9a9a8,0x2872ab64,
0xabd92c00,0xaaa72b64,0xa87229a8,0xa23e261f,0x223e0000,0x2872261f,0x2aa729a8,0x2bd92b64,0x28720000,0x2bd92b64,0x223e29a8,0xaaa7a61f,
0x2aa70000,0x223e2b64,0xabd9a9a8,0x2872a61f,0x2bd90000,0xaaa7261f,0x2872a9a8,0xa23e2b64,0x2bd90000,0xaaa7a61f,0x287229a8,0xa23eab64,
0x2aa70000,0x223eab64,0xabd929a8,0x2872261f,0x28720000,0x2bd9ab64,0x223ea9a8,0xaaa7261f,0x223e0000,0x2872a61f,0x2aa7a9a8,0x2bd9ab64,
0xabd92c00,0xaaa72b64,0xa87229a8,0xa23e261f,0xaaa72c00,0x223e261f,0x2bd9a9a8,0x2872ab64,0xa8722c00,0x2bd9a61f,0xa23ea9a8,0xaaa72b64,
0xa23e2c00,0x2872ab64,0xaaa729a8,0x2bd9a61f,0x223e2c00,0xa872ab64,0x2aa729a8,0xabd9a61f,0x28722c00,0xabd9a61f,0x223ea9a8,0x2aa72b64,
0x2aa72c00,0xa23e261f,0xabd9a9a8,0xa872ab64,0x2bd92c00,0x2aa72b64,0x287229a8,0x223e261f,0xa23e0000,0xa872261f,0xaaa729a8,0xabd92b64,
0xa8720000,0xabd92b64,0xa23e29a8,0x2aa7a61f,0xaaa70000,0xa23e2b64,0x2bd9a9a8,0xa872a61f,0xabd90000,0x2aa7261f,0xa872a9a8,0x223e2b64,
0xabd90000,0x2aa7a61f,0xa87229a8,0x223eab64,0xaaa70000,0xa23eab64,0x2bd929a8,0xa872261f,0xa8720000,0xabd9ab64,0xa23ea9a8,0x2aa7261f,
0xa23e0000,0xa872a61f,0xaaa7a9a8,0xabd9ab64,0xa23e0000,0xa872a61f,0xaaa7a9a8,0xabd9ab64,0xa8720000,0xabd9ab64,0xa23ea9a8,0x2aa7261f,
0xaaa70000,0xa23eab64,0x2bd929a8,0xa872261f,0xabd90000,0x2aa7a61f,0xa87229a8,0x223eab64,0xabd90000,0x2aa7261f,0xa872a9a8,0x223e2b64,
0xaaa70000,0xa23e2b64,0x2bd9a9a8,0xa872a61f,0xa8720000,0xabd92b64,0xa23e29a8,0x2aa7a61f,0xa23e0000,0xa872261f,0xaaa729a8,0xabd92b64,
0x2bd92c00,0x2aa72b64,0x287229a8,0x223e261f,0x2aa72c00,0xa23e261f,0xabd9a9a8,0xa872ab64,0x28722c00,0xabd9a61f,0x223ea9a8,0x2aa72b64,
0x223e2c00,0xa872ab64,0x2aa729a8,0xabd9a61f,0xa23e2c00,0x2872ab64,0xaaa729a8,0x2bd9a61f,0xa8722c00,0x2bd9a61f,0xa23ea9a8,0xaaa72b64,
0xaaa72c00,0x223e261f,0x2bd9a9a8,0x2872ab64,0xabd92c00,0xaaa72b64,0xa87229a8,0xa23e261f,0x223e0000,0x2872a61f,0x2aa7a9a8,0x2bd9ab64,
0x28720000,0x2bd9ab64,0x223ea9a8,0xaaa7261f,0x2aa70000,0x223eab64,0xabd929a8,0x2872261f,0x2bd90000,0xaaa7a61f,0x287229a8,0xa23eab64,
0x2bd90000,0xaaa7261f,0x2872a9a8,0xa23e2b64,0x2aa70000,0x223e2b64,0xabd9a9a8,0x2872a61f,0x28720000,0x2bd92b64,0x223e29a8,0xaaa7a61f,
0x223e0000,0x2872261f,0x2aa729a8,0x2bd92b64,0xabd92c00,0xaaa72b64,0xa87229a8,0xa23e261f,0xaaa72c00,0x223e261f,0x2bd9a9a8,0x2872ab64,
0xa8722c00,0x2bd9a61f,0xa23ea9a8,0xaaa72b64,0xa23e2c00,0x2872ab64,0xaaa729a8,0x2bd9a61f,0x223e2c00,0xa872ab64,0x2aa729a8,0xabd9a61f,
0x28722c00,0xabd9a61f,0x223ea9a8,0x2aa72b64,0x2aa72c00,0xa23e261f,0xabd9a9a8,0xa872ab64,0x2bd92c00,0x2aa72b64,0x287229a8,0x223e261f,
0xa23e0000,0xa872a61f,0xaaa7a9a8,0xabd9ab64,0x28720000,0x2bd92b64,0x223e29a8,0xaaa7a61f,0xaaa70000,0xa23eab64,0x2bd929a8,0xa872261f,
0x2bd90000,0xaaa7261f,0x2872a9a8,0xa23e2b64,0xabd90000,0x2aa7261f,0xa872a9a8,0x223e2b64,0x2aa70000,0x223eab64,0xabd929a8,0x2872261f,
0xa8720000,0xabd92b64,0xa23e29a8,0x2aa7a61f,0x223e0000,0x2872a61f,0x2aa7a9a8,0x2bd9ab64,0x2bd92c00,0x2aa72b64,0x287229a8,0x223e261f,
0xaaa7ac00,0x223ea61f,0x2bd929a8,0x28722b64,0x28722c00,0xabd9a61f,0x223ea9a8,0x2aa72b64,0xa23eac00,0x28722b64,0xaaa7a9a8,0x2bd9261f,
0xa23e2c00,0x2872ab64,0xaaa729a8,0x2bd9a61f,0x2872ac00,0xabd9261f,0x223e29a8,0x2aa7ab64,0xaaa72c00,0x223e261f,0x2bd9a9a8,0x2872ab64,
0x2bd9ac00,0x2aa7ab64,0x2872a9a8,0x223ea61f,0x223e0000,0x2872a61f,0x2aa7a9a8,0x2bd9ab64,0xa8720000,0xabd92b64,0xa23e29a8,0x2aa7a61f,
0x2aa70000,0x223eab64,0xabd929a8,0x2872261f,0xabd90000,0x2aa7261f,0xa872a9a8,0x223e2b64,0x2bd90000,0xaaa7261f,0x2872a9a8,0xa23e2b64,
0xaaa70000,0xa23eab64,0x2bd929a8,0xa872261f,0x28720000,0x2bd92b64,0x223e29a8,0xaaa7a61f,0xa23e0000,0xa872a61f,0xaaa7a9a8,0xabd9ab64,
0xabd92c00,0xaaa72b64,0xa87229a8,0xa23e261f,0x2aa7ac00,0xa23ea61f,0xabd929a8,0xa8722b64,0xa8722c00,0x2bd9a61f,0xa23ea9a8,0xaaa72b64,
0x223eac00,0xa8722b64,0x2aa7a9a8,0xabd9261f,0x223e2c00,0xa872ab64,0x2aa729a8,0xabd9a61f,0xa872ac00,0x2bd9261f,0xa23e29a8,0xaaa7ab64,
0x2aa72c00,0xa23e261f,0xabd9a9a8,0xa872ab64,0xabd9ac00,0xaaa7ab64,0xa872a9a8,0xa23ea61f,0xabd9ac00,0xaaa7ab64,0xa872a9a8,0xa23ea61f,
0x2aa72c00,0xa23e261f,0xabd9a9a8,0xa872ab64,0xa872ac00,0x2bd9261f,0xa23e29a8,0xaaa7ab64,0x223e2c00,0xa872ab64,0x2aa729a8,0xabd9a61f,
0x223eac00,0xa8722b64,0x2aa7a9a8,0xabd9261f,0xa8722c00,0x2bd9a61f,0xa23ea9a8,0xaaa72b64,0x2aa7ac00,0xa23ea61f,0xabd929a8,0xa8722b64,
0xabd92c00,0xaaa72b64,0xa87229a8,0xa23e261f,0xa23e0000,0xa872a61f,0xaaa7a9a8,0xabd9ab64,0x28720000,0x2bd92b64,0x223e29a8,0xaaa7a61f,
0xaaa70000,0xa23eab64,0x2bd929a8,0xa872261f,0x2bd90000,0xaaa7261f,0x2872a9a8,0xa23e2b64,0xabd90000,0x2aa7261f,0xa872a9a8,0x223e2b64,
0x2aa70000,0x223eab64,0xabd929a8,0x2872261f,0xa8720000,0xabd92b64,0xa23e29a8,0x2aa7a61f,0x223e0000,0x2872a61f,0x2aa7a9a8,0x2bd9ab64,
0x2bd9ac00,0x2aa7ab64,0x2872a9a8,0x223ea61f,0xaaa72c00,0x223e261f,0x2bd9a9a8,0x2872ab64,0x2872ac00,0xabd9261f,0x223e29a8,0x2aa7ab64,
0xa23e2c00,0x2872ab64,0xaaa729a8,0x2bd9a61f,0xa23eac00,0x28722b64,0xaaa7a9a8,0x2bd9261f,0x28722c00,0xabd9a61f,0x223ea9a8,0x2aa72b64,
0xaaa7ac00,0x223ea61f,0x2bd929a8,0x28722b64,0x2bd92c00,0x2aa72b64,0x287229a8,0x223e261f,0x223e0000,0x2872a61f,0x2aa7a9a8,0x2bd9ab64,
0xa8720000,0xabd92b64,0xa23e29a8,0x2aa7a61f,0x2aa70000,0x223eab64,0xabd929a8,0x2872261f,0xabd90000,0x2aa7261f,0xa872a9a8,0x223e2b64,
0x2bd90000,0xaaa7261f,0x2872a9a8,0xa23e2b64,0xaaa70000,0xa23eab64,0x2bd929a8,0xa872261f,0x28720000,0x2bd92b64,0x223e29a8,0xaaa7a61f,
0xa23e0000,0xa872a61f,0xaaa7a9a8,0xabd9ab64,0x27fe2800,0x96480000,0x273b2764,0xa2d7a21f,0x27ea27f6,0x9cb29a46,0x26dd270e,0xa41da38b,
0x27c327d9,0x9fc69e3e,0x266d26a7,0xa4c4a472,0x278827a8,0xa164a0a5,0x25ed262f,0xa55fa513,0x27c32800,0x9fc60000,0xa4c4a21f,0xa66da764,
0x25ed270e,0xa55fa38b,0xa73ba62f,0xa2d7a513,0x21642472,0xa788a6a7,0xa7fea7d9,0x16489e3e,0x9cb21a46,0xa7eaa7f6,0xa6dda7a8,0x241d20a5,
0x273b2800,0xa2d70000,0xa55fa764,0x25ed221f,0x1fc62513,0xa7c3a62f,0x1cb2a0a5,0x27ea27a8,0xa4c49e3e,0xa66da7d9,0x26dd2472,0x241d26a7,
0xa7fea70e,0x9648a38b,0x278827f6,0xa1641a46,0x266d2800,0xa4c40000,0x26dd221f,0x241d2764,0xa16420a5,0xa788a7a8,0x25ed27f6,0xa55f9a46,
0xa7fea6a7,0x1648a472,0xa2d71e3e,0xa73ba7d9,0x9fc6a62f,0x27c32513,0xa7eaa70e,0x1cb2a38b,0x255f2800,0xa5ed0000,0x21642764,0xa788a21f,
0xa66d9a46,0xa4c4a7f6,0xa7c3a38b,0x9fc6a70e,0xa41da7d9,0x26dd1e3e,0x9cb2a6a7,0x27ea2472,0x273b20a5,0x22d727a8,0x27fe2513,0x1648262f,
0x241d2800,0xa6dd0000,0xa7eaa21f,0x9cb2a764,0xa7fea38b,0x9648a70e,0x2164a513,0x2788262f,0x22d7a472,0x273b26a7,0x255f27d9,0xa5ed1e3e,
0x24c427f6,0xa66d1a46,0xa7c3a0a5,0x9fc6a7a8,0x21642800,0xa7880000,0x1648a764,0x27fe221f,0xa6dda62f,0x241da513,0x24c427a8,0xa66d20a5,
0x27ea1e3e,0x1cb227d9,0xa7c3a472,0x1fc6a6a7,0xa55f238b,0xa5eda70e,0x273b9a46,0x22d727f6,0x1cb22800,0xa7ea0000,0x27c3221f,0x9fc62764,
0xa2d7a7a8,0x273ba0a5,0xa7fe9a46,0x9648a7f6,0x255f26a7,0xa5ed2472,0x27889e3e,0x216427d9,0xa6dda513,0x241da62f,0xa66d238b,0xa4c4a70e,
0x96482800,0xa7fe0000,0xa2d72764,0xa73ba21f,0x1cb2a7f6,0x27ea1a46,0x241da70e,0x26dd238b,0x9fc627d9,0xa7c39e3e,0xa4c426a7,0xa66da472,
0x2164a7a8,0x278820a5,0x255fa62f,0x25ed2513,0x9fc62800,0xa7c30000,0xa66da21f,0x24c4a764,0x255fa70e,0x25ed238b,0x22d7262f,0xa73b2513,
0xa7882472,0xa164a6a7,0x1648a7d9,0x27fe9e3e,0x27ea9a46,0x9cb227f6,0xa41d27a8,0xa6dda0a5,0xa2d72800,0xa73b0000,0x25eda764,0x255f221f,
0x27c3a513,0x1fc6262f,0xa7ea20a5,0x1cb2a7a8,0xa66d9e3e,0x24c4a7d9,0x241d2472,0xa6dd26a7,0x1648270e,0xa7fe238b,0x2164a7f6,0x27889a46,
0xa4c42800,0xa66d0000,0x241d221f,0xa6dd2764,0x2788a0a5,0xa16427a8,0x255fa7f6,0x25ed1a46,0x1648a6a7,0x27fea472,0xa73b1e3e,0x22d7a7d9,
0xa7c3262f,0x9fc6a513,0x9cb2270e,0xa7ea238b,0xa5ed2800,0xa55f0000,0xa7882764,0xa164a21f,0x24c41a46,0xa66d27f6,0x1fc6238b,0xa7c3270e,
0x26dda7d9,0x241d1e3e,0x27eaa6a7,0x1cb22472,0xa2d7a0a5,0x273ba7a8,0x9648a513,0x27fea62f,0xa6dd2800,0xa41d0000,0x9cb2a21f,0x27eaa764,
0x1648238b,0xa7fe270e,0xa7882513,0x2164a62f,0x273ba472,0xa2d726a7,0xa5ed27d9,0xa55f1e3e,0x266da7f6,0x24c49a46,0x1fc620a5,0xa7c327a8,
0xa7882800,0xa1640000,0x27fea764,0x9648221f,0xa41d262f,0xa6dd2513,0x266da7a8,0x24c4a0a5,0x1cb21e3e,0xa7ea27d9,0x1fc6a472,0x27c3a6a7,
0x25eda38b,0xa55f270e,0xa2d71a46,0x273ba7f6,0xa7ea2800,0x9cb20000,0x9fc6221f,0xa7c32764,0xa73b27a8,0xa2d720a5,0x16481a46,0xa7fe27f6,
0xa5ed26a7,0xa55f2472,0x21649e3e,0xa78827d9,0xa41d2513,0xa6dd262f,0x24c4a38b,0xa66d270e,0xa7fe2800,0x16480000,0xa73b2764,0x22d7a21f,
0xa7ea27f6,0x1cb29a46,0xa6dd270e,0x241da38b,0xa7c327d9,0x1fc69e3e,0xa66d26a7,0x24c4a472,0xa78827a8,0x2164a0a5,0xa5ed262f,0x255fa513,
0xa7c32800,0x1fc60000,0x24c4a21f,0x266da764,0xa5ed270e,0x255fa38b,0x273ba62f,0x22d7a513,0xa1642472,0x2788a6a7,0x27fea7d9,0x96489e3e,
0x1cb21a46,0x27eaa7f6,0x26dda7a8,0xa41d20a5,0xa73b2800,0x22d70000,0x255fa764,0xa5ed221f,0x9fc62513,0x27c3a62f,0x9cb2a0a5,0xa7ea27a8,
0x24c49e3e,0x266da7d9,0xa6dd2472,0xa41d26a7,0x27fea70e,0x1648a38b,0xa78827f6,0x21641a46,0xa66d2800,0x24c40000,0xa6dd221f,0xa41d2764,
0x216420a5,0x2788a7a8,0xa5ed27f6,0x255f9a46,0x27fea6a7,0x9648a472,0x22d71e3e,0x273ba7d9,0x1fc6a62f,0xa7c32513,0x27eaa70e,0x9cb2a38b,
0xa55f2800,0x25ed0000,0xa1642764,0x2788a21f,0x266d9a46,0x24c4a7f6,0x27c3a38b,0x1fc6a70e,0x241da7d9,0xa6dd1e3e,0x1cb2a6a7,0xa7ea2472,
0xa73b20a5,0xa2d727a8,0xa7fe2513,0x9648262f,0xa41d2800,0x26dd0000,0x27eaa21f,0x1cb2a764,0x27fea38b,0x1648a70e,0xa164a513,0xa788262f,
0xa2d7a472,0xa73b26a7,0xa55f27d9,0x25ed1e3e,0xa4c427f6,0x266d1a46,0x27c3a0a5,0x1fc6a7a8,0xa1642800,0x27880000,0x9648a764,0xa7fe221f,
0x26dda62f,0xa41da513,0xa4c427a8,0x266d20a5,0xa7ea1e3e,0x9cb227d9,0x27c3a472,0x9fc6a6a7,0x255f238b,0x25eda70e,0xa73b9a46,0xa2d727f6,
0x9cb22800,0x27ea0000,0xa7c3221f,0x1fc62764,0x22d7a7a8,0xa73ba0a5,0x27fe9a46,0x1648a7f6,0xa55f26a7,0x25ed2472,0xa7889e3e,0xa16427d9,
0x26dda513,0xa41da62f,0x266d238b,0x24c4a70e,0x16482800,0x27fe0000,0x22d72764,0x273ba21f,0x9cb2a7f6,0xa7ea1a46,0xa41da70e,0xa6dd238b,
0x1fc627d9,0x27c39e3e,0x24c426a7,0x266da472,0xa164a7a8,0xa78820a5,0xa55fa62f,0xa5ed2513,0x1fc62800,0x27c30000,0x266da21f,0xa4c4a764,
0xa55fa70e,0xa5ed238b,0xa2d7262f,0x273b2513,0x27882472,0x2164a6a7,0x9648a7d9,0xa7fe9e3e,0xa7ea9a46,0x1cb227f6,0x241d27a8,0x26dda0a5,
0x22d72800,0x273b0000,0xa5eda764,0xa55f221f,0xa7c3a513,0x9fc6262f,0x27ea20a5,0x9cb2a7a8,0x266d9e3e,0xa4c4a7d9,0xa41d2472,0x26dd26a7,
0x9648270e,0x27fe238b,0xa164a7f6,0xa7889a46,0x24c42800,0x266d0000,0xa41d221f,0x26dd2764,0xa788a0a5,0x216427a8,0xa55fa7f6,0xa5ed1a46,
0x9648a6a7,0xa7fea472,0x273b1e3e,0xa2d7a7d9,0x27c3262f,0x1fc6a513,0x1cb2270e,0x27ea238b,0x25ed2800,0x255f0000,0x27882764,0x2164a21f,
0xa4c41a46,0x266d27f6,0x9fc6238b,0x27c3270e,0xa6dda7d9,0xa41d1e3e,0xa7eaa6a7,0x9cb22472,0x22d7a0a5,0xa73ba7a8,0x1648a513,0xa7fea62f,
0x26dd2800,0x241d0000,0x1cb2a21f,0xa7eaa764,0x9648238b,0x27fe270e,0x27882513,0xa164a62f,0xa73ba472,0x22d726a7,0x25ed27d9,0x255f1e3e,
0xa66da7f6,0xa4c49a46,0x9fc620a5,0x27c327a8,0x27882800,0x21640000,0xa7fea764,0x1648221f,0x241d262f,0x26dd2513,0xa66da7a8,0xa4c4a0a5,
0x9cb21e3e,0x27ea27d9,0x9fc6a472,0xa7c3a6a7,0xa5eda38b,0x255f270e,0x22d71a46,0xa73ba7f6,0x27ea2800,0x1cb20000,0x1fc6221f,0x27c32764,
0x273b27a8,0x22d720a5,0x96481a46,0x27fe27f6,0x25ed26a7,0x255f2472,0xa1649e3e,0x278827d9,0x241d2513,0x26dd262f,0xa4c4a38b,0x266d270e,
0x255f25a8,0xa5eda5a8,0x2164221f,0xa788a764,0x24c42513,0xa66da62f,0x1fc620a5,0xa7c3a7a8,0x241d2472,0xa6dda6a7,0x1cb21e3e,0xa7eaa7d9,
0x22d7238b,0xa73ba70e,0x16481a46,0xa7fea7f6,0xa41da5a8,0x26dd25a8,0x27ea2764,0x1cb2221f,0x9648a0a5,0x27fe27a8,0x278827f6,0xa1649a46,
0x22d71e3e,0x273b27d9,0x255f26a7,0xa5eda472,0x266d2513,0x24c4262f,0x1fc6238b,0xa7c3a70e,0x216425a8,0xa788a5a8,0x1648a21f,0x27fe2764,
0xa41d9a46,0xa6dda7f6,0x266d238b,0x24c4270e,0xa7eaa6a7,0x9cb2a472,0x27c327d9,0x9fc61e3e,0xa5eda7a8,0x255f20a5,0x22d7262f,0xa73ba513,
0x9cb2a5a8,0x27ea25a8,0xa7c3a764,0x1fc6a21f,0x273b238b,0x22d7270e,0x9648a513,0x27fe262f,0x255f27d9,0xa5ed9e3e,0x27882472,0x216426a7,
0xa41d1a46,0xa6dda7f6,0x24c427a8,0xa66da0a5,0x964825a8,0xa7fea5a8,0xa2d7221f,0xa73ba764,0xa7eaa62f,0x1cb2a513,0xa6dda7a8,0x241da0a5,
0x1fc6a472,0x27c326a7,0x24c49e3e,0x266d27d9,0x2788270e,0xa164238b,0x25ed27f6,0xa55f1a46,0x1fc6a5a8,0x27c325a8,0x266d2764,0xa4c4221f,
0x25ed27a8,0xa55f20a5,0xa73b9a46,0xa2d7a7f6,0xa7889e3e,0xa164a7d9,0x1648a6a7,0x27fe2472,0x1cb2a62f,0x27ea2513,0x26dd270e,0xa41d238b,
0xa2d725a8,0xa73ba5a8,0x25eda21f,0x255f2764,0x9fc6a7f6,0x27c31a46,0x9cb2270e,0xa7eaa38b,0x266d26a7,0xa4c42472,0xa41da7d9,0x26dd9e3e,
0xa7fea0a5,0x9648a7a8,0x27882513,0xa164262f,0x24c4a5a8,0x266d25a8,0xa41da764,0x26dda21f,0xa164270e,0xa788a38b,0x25ed262f,0xa55f2513,
0x1648a7d9,0x27fe1e3e,0xa73ba472,0x22d7a6a7,0x1fc627f6,0xa7c31a46,0x27ea20a5,0x9cb227a8,0xa5ed25a8,0xa55fa5a8,0xa788221f,0xa164a764,
0x266da513,0x24c4262f,0x27c3a0a5,0x1fc627a8,0xa6dd2472,0xa41da6a7,0xa7ea1e3e,0x9cb2a7d9,0x273ba38b,0x22d7270e,0x27fe9a46,0x164827f6,
0x26dda5a8,0x241d25a8,0x1cb22764,0xa7ea221f,0xa7fe20a5,0x9648a7a8,0x2164a7f6,0x27881a46,0x273b1e3e,0xa2d727d9,0xa5ed26a7,0xa55fa472,
0xa4c4a513,0x266da62f,0x27c3a38b,0x1fc6270e,0xa78825a8,0xa164a5a8,0x27fea21f,0x96482764,0x26dd1a46,0xa41d27f6,0xa4c4a38b,0x266da70e,
0x9cb2a6a7,0x27eaa472,0x9fc627d9,0xa7c31e3e,0xa55f27a8,0xa5eda0a5,0x273ba62f,0x22d72513,0x27eaa5a8,0x1cb225a8,0x1fc6a764,0x27c3a21f,
0xa2d7a38b,0x273ba70e,0xa7fe2513,0x9648a62f,0xa5ed27d9,0xa55f9e3e,0x21642472,0xa78826a7,0x26dd9a46,0xa41d27f6,0x266da7a8,0x24c420a5,
0xa7fe25a8,0x1648a5a8,0xa73b221f,0x22d7a764,0x9cb2262f,0xa7ea2513,0xa41d27a8,0xa6dd20a5,0x27c3a472,0x9fc626a7,0x266d9e3e,0xa4c427d9,
0x2164a70e,0x2788a38b,0x255fa7f6,0x25ed9a46,0x27c3a5a8,0x9fc625a8,0xa4c42764,0xa66d221f,0x255fa7a8,0x25eda0a5,0x22d71a46,0xa73b27f6,
0xa1649e3e,0x2788a7d9,0x27fea6a7,0x96482472,0xa7ea262f,0x1cb2a513,0x241da70e,0x26dda38b,0xa73b25a8,0x22d7a5a8,0x255fa21f,0xa5ed2764,
0xa7c327f6,0x9fc69a46,0x27eaa70e,0x9cb2238b,0xa4c426a7,0xa66d2472,0x26dda7d9,0x241d9e3e,0x164820a5,0xa7fe27a8,0x2164a513,0x2788a62f,
0x266da5a8,0xa4c425a8,0x26dda764,0x241da21f,0x2788a70e,0xa164238b,0x255fa62f,0x25eda513,0x27fea7d9,0x96481e3e,0x22d7a472,0x273ba6a7,
0x27c3a7f6,0x1fc69a46,0x1cb2a0a5,0x27eaa7a8,0xa55f25a8,0x25eda5a8,0xa164221f,0x2788a764,0xa4c42513,0x266da62f,0x9fc620a5,0x27c3a7a8,
0xa41d2472,0x26dda6a7,0x9cb21e3e,0x27eaa7d9,0xa2d7238b,0x273ba70e,0x96481a46,0x27fea7f6,0x241da5a8,0xa6dd25a8,0xa7ea2764,0x9cb2221f,
0x1648a0a5,0xa7fe27a8,0xa78827f6,0x21649a46,0xa2d71e3e,0xa73b27d9,0xa55f26a7,0x25eda472,0xa66d2513,0xa4c4262f,0x9fc6238b,0x27c3a70e,
0xa16425a8,0x2788a5a8,0x9648a21f,0xa7fe2764,0x241d9a46,0x26dda7f6,0xa66d238b,0xa4c4270e,0x27eaa6a7,0x1cb2a472,0xa7c327d9,0x1fc61e3e,
0x25eda7a8,0xa55f20a5,0xa2d7262f,0x273ba513,0x1cb2a5a8,0xa7ea25a8,0x27c3a764,0x9fc6a21f,0xa73b238b,0xa2d7270e,0x1648a513,0xa7fe262f,
0xa55f27d9,0x25ed9e3e,0xa7882472,0xa16426a7,0x241d1a46,0x26dda7f6,0xa4c427a8,0x266da0a5,0x164825a8,0x27fea5a8,0x22d7221f,0x273ba764,
0x27eaa62f,0x9cb2a513,0x26dda7a8,0xa41da0a5,0x9fc6a472,0xa7c326a7,0xa4c49e3e,0xa66d27d9,0xa788270e,0x2164238b,0xa5ed27f6,0x255f1a46,
0x9fc6a5a8,0xa7c325a8,0xa66d2764,0x24c4221f,0xa5ed27a8,0x255f20a5,0x273b9a46,0x22d7a7f6,0x27889e3e,0x2164a7d9,0x9648a6a7,0xa7fe2472,
0x9cb2a62f,0xa7ea2513,0xa6dd270e,0x241d238b,0x22d725a8,0x273ba5a8,0xa5eda21f,0xa55f2764,0x1fc6a7f6,0xa7c31a46,0x1cb2270e,0x27eaa38b,
0xa66d26a7,0x24c42472,0x241da7d9,0xa6dd9e3e,0x27fea0a5,0x1648a7a8,0xa7882513,0x2164262f,0xa4c4a5a8,0xa66d25a8,0x241da764,0xa6dda21f,
0x2164270e,0x2788a38b,0xa5ed262f,0x255f2513,0x9648a7d9,0xa7fe1e3e,0x273ba472,0xa2d7a6a7,0x9fc627f6,0x27c31a46,0xa7ea20a5,0x1cb227a8,
0x25ed25a8,0x255fa5a8,0x2788221f,0x2164a764,0xa66da513,0xa4c4262f,0xa7c3a0a5,0x9fc627a8,0x26dd2472,0x241da6a7,0x27ea1e3e,0x1cb2a7d9,
0xa73ba38b,0xa2d7270e,0xa7fe9a46,0x964827f6,0xa6dda5a8,0xa41d25a8,0x9cb22764,0x27ea221f,0x27fe20a5,0x1648a7a8,0xa164a7f6,0xa7881a46,
0xa73b1e3e,0x22d727d9,0x25ed26a7,0x255fa472,0x24c4a513,0xa66da62f,0xa7c3a38b,0x9fc6270e,0x278825a8,0x2164a5a8,0xa7fea21f,0x16482764,
0xa6dd1a46,0x241d27f6,0x24c4a38b,0xa66da70e,0x1cb2a6a7,0xa7eaa472,0x1fc627d9,0x27c31e3e,0x255f27a8,0x25eda0a5,0xa73ba62f,0xa2d72513,
0xa7eaa5a8,0x9cb225a8,0x9fc6a764,0xa7c3a21f,0x22d7a38b,0xa73ba70e,0x27fe2513,0x1648a62f,0x25ed27d9,0x255f9e3e,0xa1642472,0x278826a7,
0xa6dd9a46,0x241d27f6,0xa66da7a8,0xa4c420a5,0x27fe25a8,0x9648a5a8,0x273b221f,0xa2d7a764,0x1cb2262f,0x27ea2513,0x241d27a8,0x26dd20a5,
0xa7c3a472,0x1fc626a7,0xa66d9e3e,0x24c427d9,0xa164a70e,0xa788a38b,0xa55fa7f6,0xa5ed9a46,0xa7c3a5a8,0x1fc625a8,0x24c42764,0x266d221f,
0xa55fa7a8,0xa5eda0a5,0xa2d71a46,0x273b27f6,0x21649e3e,0xa788a7d9,0xa7fea6a7,0x16482472,0x27ea262f,0x9cb2a513,0xa41da70e,0xa6dda38b,
0x273b25a8,0xa2d7a5a8,0xa55fa21f,0x25ed2764,0x27c327f6,0x1fc69a46,0xa7eaa70e,0x1cb2238b,0x24c426a7,0x266d2472,0xa6dda7d9,0xa41d9e3e,
0x964820a5,0x27fe27a8,0xa164a513,0xa788a62f,0xa66da5a8,0x24c425a8,0xa6dda764,0xa41da21f,0xa788a70e,0x2164238b,0xa55fa62f,0xa5eda513,
0xa7fea7d9,0x16481e3e,0xa2d7a472,0xa73ba6a7,0xa7c3a7f6,0x9fc69a46,0x9cb2a0a5,0xa7eaa7a8,
};

#define PROF(slot) do {} while (0)
#define PROF3(slot) do {} while (0)
#define PROF2(slot) do {} while (0)

__device__ __forceinline__ uint32_t smem_u32(const void* p) { return (uint32_t)__cvta_generic_to_shared(p); }

__device__ __forceinline__ void mbar_init(uint32_t a, uint32_t c) {
  asm volatile("mbarrier.init.shared::cta.b64 [%0], %1;\n" ::"r"(a), "r"(c) : "memory");
}
__device__ __forceinline__ void mbar_expect_tx(uint32_t a, uint32_t bytes) {
  asm volatile("mbarrier.arrive.expect_tx.shared::cta.b64 _, [%0], %1;\n" ::"r"(a), "r"(bytes) : "memory");
}
__device__ __forceinline__ void mbar_arrive_cluster(uint32_t cluster_addr) {
  asm volatile("mbarrier.arrive.shared::cluster.b64 _, [%0];\n" ::"r"(cluster_addr) : "memory");
}
__device__ __forceinline__ void mbar_arrive_cluster_n(uint32_t cluster_addr, uint32_t n) {
  asm volatile("mbarrier.arrive.shared::cluster.b64 _, [%0], %1;\n" ::"r"(cluster_addr), "r"(n) : "memory");
}
__device__ __forceinline__ bool mbar_try(uint32_t a, uint32_t parity) {
  uint32_t ok;
  asm volatile("{\n.reg .pred p;\nmbarrier.try_wait.parity.shared::cta.b64 p, [%1], %2;\nselp.u32 %0, 1, 0, p;\n}\n"
               : "=r"(ok) : "r"(a), "r"(parity) : "memory");
  return ok;
}
__device__ __forceinline__ void mbar_wait(uint32_t a, uint32_t parity) {
  if (mbar_try(a, parity)) return;
#pragma unroll 1
  for (int n = 0; n < SPIN_LIMIT; n++)
    if (mbar_try(a, parity)) break;
}
__device__ __forceinline__ bool elect_one() {
  uint32_t p;
  asm volatile("{\n.reg .pred P;\nelect.sync _|P, 0xffffffff;\nselp.u32 %0, 1, 0, P;\n}\n" : "=r"(p));
  return p;
}
__device__ __forceinline__ uint32_t mapa(uint32_t a, uint32_t rank) {
  uint32_t r;
  asm volatile("mapa.shared::cluster.u32 %0, %1, %2;\n" : "=r"(r) : "r"(a), "r"(rank));
  return r;
}
__device__ __forceinline__ void nb_sync(int id, int n) { asm volatile("bar.sync %0, %1;\n" ::"r"(id), "r"(n) : "memory"); }
__device__ __forceinline__ void nb_arrive(int id, int n) { asm volatile("bar.arrive %0, %1;\n" ::"r"(id), "r"(n) : "memory"); }
__device__ __forceinline__ void cluster_sync_all() {
  asm volatile("barrier.cluster.arrive.relaxed.aligned;\nbarrier.cluster.wait.aligned;\n" ::: "memory");
}
__device__ __forceinline__ void fence_async_smem() { asm volatile("fence.proxy.async.shared::cta;\n" ::: "memory"); }
__device__ __forceinline__ void fence_async_all() { asm volatile("fence.proxy.async.global;\n" ::: "memory"); }

__device__ __forceinline__ void tma_load_3d(uint32_t dst, const CUtensorMap* tm, uint32_t bar, int c0, int c1, int c2) {
  asm volatile(
      "cp.async.bulk.tensor.3d.shared::cluster.global.mbarrier::complete_tx::bytes [%0], [%1, {%3, %4, %5}], [%2];\n"
      ::"r"(dst), "l"(tm), "r"(bar), "r"(c0), "r"(c1), "r"(c2) : "memory");
}
__device__ __forceinline__ void tma_load_4d(uint32_t dst, const CUtensorMap* tm, uint32_t bar, int c0, int c1, int c2, int c3) {
  asm volatile(
      "cp.async.bulk.tensor.4d.shared::cluster.global.mbarrier::complete_tx::bytes [%0], [%1, {%3, %4, %5, %6}], [%2];\n"
      ::"r"(dst), "l"(tm), "r"(bar), "r"(c0), "r"(c1), "r"(c2), "r"(c3) : "memory");
}
__device__ __forceinline__ void tma_load_3d_mc(uint32_t dst, const CUtensorMap* tm, uint32_t bar, int c0, int c1, int c2) {
  asm volatile(
      "cp.async.bulk.tensor.3d.shared::cluster.global.mbarrier::complete_tx::bytes.multicast::cluster [%0], [%1, {%3, %4, %5}], [%2], %6;\n"
      ::"r"(dst), "l"(tm), "r"(bar), "r"(c0), "r"(c1), "r"(c2), "h"((uint16_t)3) : "memory");
}
__device__ __forceinline__ void tma_load_5d(uint32_t dst, const CUtensorMap* tm, uint32_t bar, int c0, int c4) {
  asm volatile(
      "cp.async.bulk.tensor.5d.shared::cluster.global.mbarrier::complete_tx::bytes [%0], [%1, {%3, %5, %5, %5, %4}], [%2];\n"
      ::"r"(dst), "l"(tm), "r"(bar), "r"(c0), "r"(c4), "r"(0) : "memory");
}
__device__ __forceinline__ void bulk_load(uint32_t dst, const void* src, uint32_t bytes, uint32_t bar) {
  asm volatile("cp.async.bulk.shared::cluster.global.mbarrier::complete_tx::bytes [%0], [%1], %2, [%3];\n"
               ::"r"(dst), "l"(src), "r"(bytes), "r"(bar) : "memory");
}
__device__ __forceinline__ void bulk_commit() { asm volatile("cp.async.bulk.commit_group;\n" ::: "memory"); }
__device__ __forceinline__ void bulk_wait0() { asm volatile("cp.async.bulk.wait_group 0;\n" ::: "memory"); }
__device__ __forceinline__ void prefetch_tmap(const CUtensorMap* tm) {
  asm volatile("prefetch.tensormap [%0];\n" ::"l"(tm) : "memory");
}

__device__ __forceinline__ void wg_fence() { asm volatile("wgmma.fence.sync.aligned;\n" ::: "memory"); }
__device__ __forceinline__ void wg_commit() { asm volatile("wgmma.commit_group.sync.aligned;\n" ::: "memory"); }
template <int N> __device__ __forceinline__ void wg_wait() {
  asm volatile("wgmma.wait_group.sync.aligned %0;\n" ::"n"(N) : "memory");
}
__device__ __forceinline__ uint64_t mkdesc(uint32_t addr, uint32_t lbo, uint32_t sbo, uint32_t swz) {
  return (uint64_t)((addr & 0x3FFFF) >> 4) | ((uint64_t)(lbo >> 4) << 16) | ((uint64_t)(sbo >> 4) << 32) |
         ((uint64_t)swz << 62);
}

#define R4(d, o) "+f"(d[o + 0]), "+f"(d[o + 1]), "+f"(d[o + 2]), "+f"(d[o + 3])
#define R8(d, o) R4(d, o), R4(d, o + 4)
#define R16(d, o) R8(d, o), R8(d, o + 8)
#define R32(d, o) R16(d, o), R16(d, o + 16)
#define R64(d, o) R32(d, o), R32(d, o + 32)

__device__ __forceinline__ void wgmma_n192(float (&d)[96], uint64_t da, uint64_t db, uint32_t acc) {
  asm volatile(
      "{\n.reg .pred p;\nsetp.ne.u32 p, %98, 0;\n"
      "wgmma.mma_async.sync.aligned.m64n192k16.f32.bf16.bf16 "
      "{%0,%1,%2,%3,%4,%5,%6,%7,%8,%9,%10,%11,%12,%13,%14,%15,%16,%17,%18,%19,%20,%21,%22,%23,%24,%25,%26,%27,%28,%29,%30,%31,"
      "%32,%33,%34,%35,%36,%37,%38,%39,%40,%41,%42,%43,%44,%45,%46,%47,%48,%49,%50,%51,%52,%53,%54,%55,%56,%57,%58,%59,%60,%61,%62,%63,"
      "%64,%65,%66,%67,%68,%69,%70,%71,%72,%73,%74,%75,%76,%77,%78,%79,%80,%81,%82,%83,%84,%85,%86,%87,%88,%89,%90,%91,%92,%93,%94,%95}, "
      "%96, %97, p, 1, 1, 0, 1;\n}\n"
      : R64(d, 0), R32(d, 64)
      : "l"(da), "l"(db), "r"(acc));
}
__device__ __forceinline__ void wgmma_n128(float (&d)[64], uint64_t da, uint64_t db, uint32_t acc) {
  asm volatile(
      "{\n.reg .pred p;\nsetp.ne.u32 p, %66, 0;\n"
      "wgmma.mma_async.sync.aligned.m64n128k16.f32.bf16.bf16 "
      "{%0,%1,%2,%3,%4,%5,%6,%7,%8,%9,%10,%11,%12,%13,%14,%15,%16,%17,%18,%19,%20,%21,%22,%23,%24,%25,%26,%27,%28,%29,%30,%31,"
      "%32,%33,%34,%35,%36,%37,%38,%39,%40,%41,%42,%43,%44,%45,%46,%47,%48,%49,%50,%51,%52,%53,%54,%55,%56,%57,%58,%59,%60,%61,%62,%63}, "
      "%64, %65, p, 1, 1, 0, 1;\n}\n"
      : R64(d, 0)
      : "l"(da), "l"(db), "r"(acc));
}
template <int N> __device__ __forceinline__ void fence_regs(float (&d)[N]) {
#pragma unroll
  for (int i = 0; i < N; i++) asm volatile("" : "+f"(d[i])::"memory");
}

__device__ __forceinline__ void mma16816(float (&d)[4], uint32_t a0, uint32_t a1, uint32_t a2, uint32_t a3, uint32_t b0,
                                         uint32_t b1) {
  asm("mma.sync.aligned.m16n8k16.row.col.f32.bf16.bf16.f32 {%0,%1,%2,%3}, {%4,%5,%6,%7}, {%8,%9}, {%0,%1,%2,%3};\n"
      : "+f"(d[0]), "+f"(d[1]), "+f"(d[2]), "+f"(d[3])
      : "r"(a0), "r"(a1), "r"(a2), "r"(a3), "r"(b0), "r"(b1));
}
__device__ __forceinline__ void mma16816_z(float (&d)[4], uint32_t a0, uint32_t a1, uint32_t a2, uint32_t a3, uint32_t b0,
                                           uint32_t b1) {
  asm("mma.sync.aligned.m16n8k16.row.col.f32.bf16.bf16.f32 {%0,%1,%2,%3}, {%4,%5,%6,%7}, {%8,%9}, {%10,%10,%10,%10};\n"
      : "=f"(d[0]), "=f"(d[1]), "=f"(d[2]), "=f"(d[3])
      : "r"(a0), "r"(a1), "r"(a2), "r"(a3), "r"(b0), "r"(b1), "f"(0.f));
}
__device__ __forceinline__ void ldsm4t(uint32_t (&r)[4], uint32_t a) {
  asm volatile("ldmatrix.sync.aligned.m8n8.x4.trans.shared.b16 {%0,%1,%2,%3}, [%4];\n"
               : "=r"(r[0]), "=r"(r[1]), "=r"(r[2]), "=r"(r[3]) : "r"(a) : "memory");
}
__device__ __forceinline__ void ldsm2t(uint32_t& r0, uint32_t& r1, uint32_t a) {
  asm volatile("ldmatrix.sync.aligned.m8n8.x2.trans.shared.b16 {%0,%1}, [%2];\n" : "=r"(r0), "=r"(r1) : "r"(a) : "memory");
}
__device__ __forceinline__ void st_async128(uint32_t a, uint32_t bar, uint32_t x, uint32_t y, uint32_t z, uint32_t w) {
  asm volatile("st.async.weak.shared::cluster.mbarrier::complete_tx::bytes.v4.b32 [%0], {%2,%3,%4,%5}, [%1];\n"
               ::"r"(a), "r"(bar), "r"(x), "r"(y), "r"(z), "r"(w) : "memory");
}
__device__ __forceinline__ void mbar_arrive(uint32_t a) {
  asm volatile("mbarrier.arrive.shared::cta.b64 _, [%0];\n" ::"r"(a) : "memory");
}
__device__ __forceinline__ void stsm4(uint32_t a, uint32_t r0, uint32_t r1, uint32_t r2, uint32_t r3) {
  asm volatile("stmatrix.sync.aligned.m8n8.x4.shared.b16 [%0], {%1,%2,%3,%4};\n"
               ::"r"(a), "r"(r0), "r"(r1), "r"(r2), "r"(r3) : "memory");
}
__device__ __forceinline__ void stsm4t(uint32_t a, uint32_t r0, uint32_t r1, uint32_t r2, uint32_t r3) {
  asm volatile("stmatrix.sync.aligned.m8n8.x4.trans.shared.b16 [%0], {%1,%2,%3,%4};\n"
               ::"r"(a), "r"(r0), "r"(r1), "r"(r2), "r"(r3) : "memory");
}
__device__ __forceinline__ uint2 lds64(uint32_t a) {
  uint2 v;
  asm volatile("ld.shared.v2.u32 {%0,%1}, [%2];\n" : "=r"(v.x), "=r"(v.y) : "r"(a));
  return v;
}
__device__ __forceinline__ uint4 lds128(uint32_t a) {
  uint4 v;
  asm volatile("ld.shared.v4.u32 {%0,%1,%2,%3}, [%4];\n" : "=r"(v.x), "=r"(v.y), "=r"(v.z), "=r"(v.w) : "r"(a) : "memory");
  return v;
}
__device__ __forceinline__ void sts128(uint32_t a, uint32_t x, uint32_t y, uint32_t z, uint32_t w) {
  asm volatile("st.shared.v4.u32 [%0], {%1,%2,%3,%4};\n" ::"r"(a), "r"(x), "r"(y), "r"(z), "r"(w) : "memory");
}
__device__ __forceinline__ uint32_t pack_bf16(float lo, float hi) {
  uint32_t r;
  asm("cvt.rn.bf16x2.f32 %0, %1, %2;\n" : "=r"(r) : "f"(hi), "f"(lo));
  return r;
}
__device__ __forceinline__ uint32_t bmul2(uint32_t a, uint32_t b) {
  uint32_t r;
  asm("mul.rn.bf16x2 %0, %1, %2;\n" : "=r"(r) : "r"(a), "r"(b));
  return r;
}
__device__ __forceinline__ uint32_t bmax2(uint32_t a, uint32_t b) {
  uint32_t r;
  asm("max.bf16x2 %0, %1, %2;\n" : "=r"(r) : "r"(a), "r"(b));
  return r;
}
__device__ __forceinline__ uint32_t bfma2(uint32_t a, uint32_t b, uint32_t c) {
  uint32_t r;
  asm("fma.rn.bf16x2 %0, %1, %2, %3;\n" : "=r"(r) : "r"(a), "r"(b), "r"(c));
  return r;
}
__device__ __forceinline__ uint32_t badd2(uint32_t a, uint32_t b) {
  uint32_t r;
  asm("add.rn.bf16x2 %0, %1, %2;\n" : "=r"(r) : "r"(a), "r"(b));
  return r;
}
__device__ __forceinline__ void prefetch_l2(const void* p) { asm volatile("prefetch.global.L2 [%0];\n" ::"l"(p)); }
__device__ __forceinline__ void cp_async16n(uint32_t dst, const void* src) {
  asm volatile("cp.async.cg.shared.global [%0], [%1], 16;\n" ::"r"(dst), "l"(src) : "memory");
}
__device__ __forceinline__ void cp_async16(uint32_t dst, const void* src, uint32_t srcbytes) {
  asm volatile("cp.async.cg.shared.global.L2::256B [%0], [%1], 16, %2;\n" ::"r"(dst), "l"(src), "r"(srcbytes) : "memory");
}
__device__ __forceinline__ uint32_t ld_acquire(const uint32_t* p) {
  uint32_t v;
  asm volatile("ld.acquire.gpu.global.u32 %0, [%1];\n" : "=r"(v) : "l"(p) : "memory");
  return v;
}
__device__ __forceinline__ uint32_t ld_relaxed(const uint32_t* p) {
  uint32_t v;
  asm volatile("ld.relaxed.gpu.global.u32 %0, [%1];\n" : "=r"(v) : "l"(p) : "memory");
  return v;
}
__device__ __forceinline__ void st_release(uint32_t* p, uint32_t v) {
  asm volatile("st.release.gpu.global.u32 [%0], %1;\n" ::"l"(p), "r"(v) : "memory");
}
__device__ __forceinline__ void wait_flag(const uint32_t* p, uint32_t want) {
  int n = 0;
  while (ld_relaxed(p) != want && ++n < SPIN_LIMIT) __nanosleep(40);
  (void)ld_acquire(p);
}

struct Params {
  const __nv_bfloat16* x;
  const __nv_bfloat16* w;
  const __nv_bfloat16* q;
  const __nv_bfloat16* k;
  const __nv_bfloat16* v;
  const __nv_bfloat16* shift_k;
  const __nv_bfloat16* ssm_k;
  const __nv_bfloat16* ssm_D;
  const __nv_bfloat16* wo;
  __nv_bfloat16* out;
};

__device__ __forceinline__ uint32_t lds32(uint32_t a) {
  uint32_t v;
  asm volatile("ld.shared.u32 %0, [%1];\n" : "=r"(v) : "r"(a));
  return v;
}
#define W4(d, o) "=f"(d[o + 0]), "=f"(d[o + 1]), "=f"(d[o + 2]), "=f"(d[o + 3])
#define W8(d, o) W4(d, o), W4(d, o + 4)
#define W16(d, o) W8(d, o), W8(d, o + 8)
#define U4(c, d, o) c(d[o + 0]), c(d[o + 1]), c(d[o + 2]), c(d[o + 3])
#define U8(c, d, o) U4(c, d, o), U4(c, d, o + 4)
#define U16(c, d, o) U8(c, d, o), U8(c, d, o + 8)
#define U32(c, d, o) U16(c, d, o), U16(c, d, o + 16)
#define D32 "{%0,%1,%2,%3,%4,%5,%6,%7,%8,%9,%10,%11,%12,%13,%14,%15,%16,%17,%18,%19,%20,%21,%22,%23,%24,%25,%26,%27,%28,%29,%30,%31}"
#define D16 "{%0,%1,%2,%3,%4,%5,%6,%7,%8,%9,%10,%11,%12,%13,%14,%15}"
#define D8 "{%0,%1,%2,%3,%4,%5,%6,%7}"
template <int ACC> __device__ __forceinline__ void hmma_n128t(uint32_t (&d)[32], const uint32_t (&a)[4], uint64_t db) {
  if (ACC)
    asm volatile("wgmma.mma_async.sync.aligned.m64n128k16.f16.f16.f16 " D32 ", {%32,%33,%34,%35}, %36, 1, 1, 1, 1;\n"
                 : U32("+r", d, 0) : "r"(a[0]), "r"(a[1]), "r"(a[2]), "r"(a[3]), "l"(db));
  else
    asm volatile("wgmma.mma_async.sync.aligned.m64n128k16.f16.f16.f16 " D32 ", {%32,%33,%34,%35}, %36, 0, 1, 1, 1;\n"
                 : U32("=r", d, 0) : "r"(a[0]), "r"(a[1]), "r"(a[2]), "r"(a[3]), "l"(db));
}
template <int ACC, int TB> __device__ __forceinline__ void hmma_n32(uint32_t (&d)[8], const uint32_t (&a)[4], uint64_t db) {
  if (ACC)
    asm volatile("wgmma.mma_async.sync.aligned.m64n32k16.f16.f16.f16 " D8 ", {%8,%9,%10,%11}, %12, 1, 1, 1, %13;\n"
                 : U8("+r", d, 0) : "r"(a[0]), "r"(a[1]), "r"(a[2]), "r"(a[3]), "l"(db), "n"(TB));
  else
    asm volatile("wgmma.mma_async.sync.aligned.m64n32k16.f16.f16.f16 " D8 ", {%8,%9,%10,%11}, %12, 0, 1, 1, %13;\n"
                 : U8("=r", d, 0) : "r"(a[0]), "r"(a[1]), "r"(a[2]), "r"(a[3]), "l"(db), "n"(TB));
}
template <int ACC> __device__ __forceinline__ void fmma_n32t(float (&d)[16], const uint32_t (&a)[4], uint64_t db) {
  if (ACC)
    asm volatile("wgmma.mma_async.sync.aligned.m64n32k16.f32.f16.f16 " D16 ", {%16,%17,%18,%19}, %20, 1, 1, 1, 1;\n"
                 : R16(d, 0) : "r"(a[0]), "r"(a[1]), "r"(a[2]), "r"(a[3]), "l"(db));
  else
    asm volatile("wgmma.mma_async.sync.aligned.m64n32k16.f32.f16.f16 " D16 ", {%16,%17,%18,%19}, %20, 0, 1, 1, 1;\n"
                 : W16(d, 0) : "r"(a[0]), "r"(a[1]), "r"(a[2]), "r"(a[3]), "l"(db));
}
template <int N> __device__ __forceinline__ void fence_regs(uint32_t (&d)[N]) {
#pragma unroll
  for (int i = 0; i < N; i++) asm volatile("" : "+r"(d[i])::"memory");
}
__device__ __forceinline__ uint32_t hmul(uint32_t a, uint32_t b) { uint32_t r; asm("mul.rn.f16x2 %0, %1, %2;\n" : "=r"(r) : "r"(a), "r"(b)); return r; }
__device__ __forceinline__ uint32_t hadd(uint32_t a, uint32_t b) { uint32_t r; asm("add.rn.f16x2 %0, %1, %2;\n" : "=r"(r) : "r"(a), "r"(b)); return r; }
__device__ __forceinline__ uint32_t hsub(uint32_t a, uint32_t b) { uint32_t r; asm("sub.rn.f16x2 %0, %1, %2;\n" : "=r"(r) : "r"(a), "r"(b)); return r; }
__device__ __forceinline__ uint32_t hfma(uint32_t a, uint32_t b, uint32_t c) { uint32_t r; asm("fma.rn.f16x2 %0, %1, %2, %3;\n" : "=r"(r) : "r"(a), "r"(b), "r"(c)); return r; }
__device__ __forceinline__ uint32_t hfnma(uint32_t a, uint32_t b, uint32_t c) {
  uint32_t r;
  asm("{\n.reg .b32 t;\nneg.f16x2 t, %1;\nfma.rn.f16x2 %0, t, %2, %3;\n}\n" : "=r"(r) : "r"(a), "r"(b), "r"(c));
  return r;
}
__device__ __forceinline__ uint32_t hrefl(uint32_t p, uint32_t s) {
  uint32_t r;
  asm("{\n.reg .b32 t;\nneg.f16x2 t, %2;\nfma.rn.f16x2 %0, %1, %3, t;\n}\n" : "=r"(r) : "r"(p), "r"(s), "r"(0x40004000u));
  return r;
}
__device__ __forceinline__ void bfly(uint32_t xr, uint32_t xi, uint32_t tr, uint32_t ti, uint32_t yr, uint32_t yi, uint32_t ur,
                                     uint32_t ui, uint32_t& sr, uint32_t& si, uint32_t& dr, uint32_t& di) {
  const uint32_t pr = hfnma(xi, ti, hmul(xr, tr)), pi = hfma(xi, tr, hmul(xr, ti));
  sr = hfnma(yi, ui, hfma(yr, ur, pr));
  si = hfma(yi, ur, hfma(yr, ui, pi));
  dr = hrefl(pr, sr);
  di = hrefl(pi, si);
}
template <int BH> __device__ __forceinline__ void fft_e1(const uint32_t (&d)[32], const uint32_t (&tw)[16], uint32_t (&a2)[2][2][4]) {
#pragma unroll
  for (int be = 0; be < 2; be++)
#pragma unroll
    for (int s = 0; s < 2; s++) {
      const int o = 16 * s + 8 * be + 2 * BH, p = 2 * BH;
      bfly(d[o], d[o + 1], tw[p], tw[p + 1], d[o + 4], d[o + 5], tw[p + 4], tw[p + 5], a2[be][0][s], a2[be][0][2 + s],
           a2[be][1][s], a2[be][1][2 + s]);
    }
}
__device__ __forceinline__ uint32_t hfms(uint32_t a, uint32_t b, uint32_t c) {
  uint32_t r;
  asm("{\n.reg .b32 t;\nneg.f16x2 t, %3;\nfma.rn.f16x2 %0, %1, %2, t;\n}\n" : "=r"(r) : "r"(a), "r"(b), "r"(c));
  return r;
}
template <int C, int J> __device__ __forceinline__ void fft_e2(const uint32_t (&d0)[8], const uint32_t (&d1)[8], uint32_t (&a3)[2][4]) {
  const uint32_t ur = d0[2 * J], ui = d0[4 + 2 * J], hr = d0[2 * J + 1], hi = d0[5 + 2 * J];
  const uint32_t vr = d1[2 * J], vi = d1[4 + 2 * J], gr = d1[2 * J + 1], gi = d1[5 + 2 * J];
  const uint32_t pr = hfnma(ui, hi, hmul(ur, hr)), pi = hfma(ui, hr, hmul(ur, hi));
  a3[0][2 + C] = pr;
  a3[0][C] = pi;
  a3[1][2 + C] = hfnma(vi, hi, hfma(vr, hr, hfnma(ui, gi, hfms(ur, gr, pi))));
  a3[1][C] = hfma(vi, hr, hfma(vr, hi, hfma(ui, gr, hfma(ur, gi, pr))));
}
__device__ __forceinline__ void fft_e3(const uint32_t (&d)[2][8], const uint32_t (&tw)[16], uint32_t zaddr) {
#pragma unroll
  for (int rho = 0; rho < 2; rho++) {
    uint32_t zr[4], zi[4];
#pragma unroll
    for (int nb = 0; nb < 4; nb++) {
      const uint32_t xi = d[nb >> 1][2 * (nb & 1) + rho], xr = d[nb >> 1][4 + 2 * (nb & 1) + rho];
      const uint32_t tr = tw[8 + 4 * rho + 2 * (nb & 1)], ti = tw[9 + 4 * rho + 2 * (nb & 1)];
      zr[nb] = hfnma(xi, ti, hmul(xr, tr));
      zi[nb] = hfma(xi, tr, hmul(xr, ti));
    }
    stsm4(zaddr + rho * 1024, zr[0], zr[1], zr[2], zr[3]);
    stsm4(zaddr + rho * 1024 + 512, zi[0], zi[1], zi[2], zi[3]);
  }
}
__device__ __forceinline__ float bf_lo(uint32_t v) {
  uint32_t r;
  asm("prmt.b32 %0, %1, 0, 0x1044;\n" : "=r"(r) : "r"(v));
  return __uint_as_float(r);
}
__device__ __forceinline__ float bf_hi(uint32_t v) { return __uint_as_float(v & 0xffff0000u); }
__device__ __forceinline__ float ex2(float x) {
  float r;
  asm("ex2.approx.ftz.f32 %0, %1;\n" : "=f"(r) : "f"(x));
  return r;
}
__device__ __forceinline__ float rcp(float x) {
  float r;
  asm("rcp.approx.ftz.f32 %0, %1;\n" : "=f"(r) : "f"(x));
  return r;
}

__device__ __forceinline__ int g2_a(int s) { return ((0xA1054 >> (4 * s)) & 15) * 16384; }
__device__ __forceinline__ int g2_b(int s) { return ((0xCDB32 >> (4 * s)) & 15) * 16384; }
static_assert(OFF_U == 10 * 16384 && OFF_H == 12 * 16384 && OFF_OP == 4 * 16384, "units");
__device__ __forceinline__ int y_slot(int wg, int it) {
  static_assert(T_B2 == T_TW + 8192 && T_A1 == T_B2 + 4096, "y slots");
  return OFF_T + T_TW + ((it + 3) & 3) * 4096 + wg * 2048;
}

__device__ __forceinline__ void to_arr(uint32_t (&d)[4], uint4 v) { d[0] = v.x; d[1] = v.y; d[2] = v.z; d[3] = v.w; }

__device__ __forceinline__ void attn_stage(uint32_t sb, int blk, int lane, const float (&acc)[96], uint32_t (&k1)[2][4]) {
  const int lr = lane & 7, lm = lane >> 3;
  const uint32_t base = sb + OFF_VP + (blk * 16 + lr + 8 * (lm & 1)) * 128;
#pragma unroll
  for (int i = 0; i < 8; i++) k1[i >> 2][i & 3] = pack_bf16(acc[34 + 4 * i], acc[35 + 4 * i]);
  const uint32_t kh = sb + OFF_KH + blk * 2048 + lane * 16;
  sts128(kh, k1[0][0], k1[0][1], k1[0][2], k1[0][3]);
  sts128(kh + 512, k1[1][0], k1[1][1], k1[1][2], k1[1][3]);
#pragma unroll
  for (int j = 0; j < 8; j += 2)
    stsm4(base + (((j + (lm >> 1)) ^ lr) << 4), pack_bf16(acc[64 + 4 * j], acc[65 + 4 * j]),
          pack_bf16(acc[66 + 4 * j], acc[67 + 4 * j]), pack_bf16(acc[68 + 4 * j], acc[69 + 4 * j]),
          pack_bf16(acc[70 + 4 * j], acc[71 + 4 * j]));
}
__device__ __forceinline__ void attn_pack(const float (&acc)[96], uint32_t (&qa)[2][8], uint32_t (&k0)[2][4]) {
#pragma unroll
  for (int hd = 0; hd < 2; hd++) {
#pragma unroll
    for (int i = 0; i < 8; i++) {
      asm volatile("cvt.rn.bf16x2.f32 %0, %1, %2;\n" : "=r"(qa[hd][i]) : "f"(acc[16 * hd + 2 * i + 1]), "f"(acc[16 * hd + 2 * i]));
    }
#pragma unroll
    for (int i = 0; i < 4; i++) {
      asm volatile("cvt.rn.bf16x2.f32 %0, %1, %2;\n" : "=r"(k0[hd][i]) : "f"(acc[33 + 16 * hd + 4 * i]), "f"(acc[32 + 16 * hd + 4 * i]));
    }
  }
}
__device__ __forceinline__ void attn_own(const uint32_t (&k0)[2][4], const uint32_t (&k1)[2][4], bool le0, bool le1,
                                         const uint32_t (&qa)[2][8], float (&l)[2][4]) {
#pragma unroll
  for (int hd = 0; hd < 2; hd++) {
    float s0[4], s1[4];
    mma16816_z(s0, qa[hd][0], qa[hd][1], qa[hd][2], qa[hd][3], k0[hd][0], k0[hd][1]);
    mma16816_z(s1, qa[hd][0], qa[hd][1], qa[hd][2], qa[hd][3], k1[hd][0], k1[hd][1]);
    mma16816(s0, qa[hd][4], qa[hd][5], qa[hd][6], qa[hd][7], k0[hd][2], k0[hd][3]);
    mma16816(s1, qa[hd][4], qa[hd][5], qa[hd][6], qa[hd][7], k1[hd][2], k1[hd][3]);
    l[hd][0] = s0[0];
    l[hd][1] = s0[1];
    l[hd][2] = le0 ? s1[2] : s0[2];
    l[hd][3] = le1 ? s1[3] : s0[3];
  }
}
template <int N> __device__ __forceinline__ void quad_softmax(float (&x)[N][2], uint32_t (&pp)[N]) {
  const float c2 = 1.4426950408889634f;
  uint32_t q[N], mx[N / 2];
#pragma unroll
  for (int n = 0; n < N; n++) {
    const uint32_t r = pack_bf16(x[n][0], x[n][1]);
    q[n] = bfma2(r, 0x3e353e35u, bmul2(r, 0x379e379eu));
    x[n][0] = bf_lo(q[n]);
    x[n][1] = bf_hi(q[n]);
  }
#pragma unroll
  for (int n = 0; n < N / 2; n++)
    mx[n] = bmax2(__byte_perm(q[2 * n], q[2 * n + 1], 0x5410), __byte_perm(q[2 * n], q[2 * n + 1], 0x7632));
#pragma unroll
  for (int o = 1; o <= 2; o++)
#pragma unroll
    for (int n = 0; n < N / 2; n++) mx[n] = bmax2(mx[n], __shfl_xor_sync(0xffffffffu, mx[n], o));
  float m[N], t[N];
#pragma unroll
  for (int n = 0; n < N / 2; n++) {
    m[2 * n] = bf_lo(mx[n]);
    m[2 * n + 1] = bf_hi(mx[n]);
  }
#pragma unroll
  for (int n = 0; n < N; n++) {
    const float nm = -m[n] * c2;
    x[n][0] = ex2(fmaf(x[n][0], c2, nm));
    x[n][1] = ex2(fmaf(x[n][1], c2, nm));
    t[n] = x[n][0] + x[n][1];
  }
#pragma unroll
  for (int o = 1; o <= 2; o++)
#pragma unroll
    for (int n = 0; n < N; n++) t[n] += __shfl_xor_sync(0xffffffffu, t[n], o);
#pragma unroll
  for (int n = 0; n < N; n++) {
    const float inv = rcp(t[n]);
    pp[n] = pack_bf16(x[n][0] * inv, x[n][1] * inv);
  }
}
__device__ __forceinline__ void attn_pv(uint32_t dst, const uint32_t (&va)[4], const uint32_t (&vb)[4], uint32_t pp,
                                        uint32_t maskLE) {
  const uint32_t b0 = pp & ~maskLE, b1 = pp & maskLE;
  float oa[4], ob[4];
  mma16816_z(oa, va[0], va[1], va[2], va[3], b0, b1);
  mma16816_z(ob, vb[0], vb[1], vb[2], vb[3], b0, b1);
  stsm4t(dst, pack_bf16(oa[0], oa[1]), pack_bf16(oa[2], oa[3]), pack_bf16(ob[0], ob[1]), pack_bf16(ob[2], ob[3]));
}

template <int MODE>
__global__ void __cluster_dims__(2, 1, 1) __launch_bounds__(NTHREADS, 1)
fused_kernel(const Params p, const __grid_constant__ CUtensorMap tmX, const __grid_constant__ CUtensorMap tmW,
             const __grid_constant__ CUtensorMap tmWo,
             const __grid_constant__ CUtensorMap tmQ,
             const __grid_constant__ CUtensorMap tmXh, const __grid_constant__ CUtensorMap tmWh) {
  extern __shared__ __align__(1024) uint8_t smem[];
  const uint32_t sb = smem_u32(smem);
  const uint32_t bars = sb + OFF_BAR;
  const int tid = threadIdx.x, lane = tid & 31, warp = __shfl_sync(0xffffffffu, tid >> 5, 0);
  const int rank = blockIdx.x & 1;
  const bool halo_cta = blockIdx.x < 4;
  if (halo_cta && MODE != 0) return;
  int grp, mem;
  {
    const int t = (blockIdx.x >> 1) - 4, u = t - 32;
    const int q7 = (u * 37) >> 8;
    const bool lo = (unsigned)t < 32u, mid = (unsigned)u < 28u;
    grp = lo ? (t & 7) : (mid ? 1 + u - 7 * q7 : 0);
    mem = lo ? (t >> 3) : (mid ? 4 + q7 : (t < 0 ? t + 6 : t - 54));
  }
  const int rg = (grp >> 2) * 4 + (mem >> 1), hp = (grp & 3) * 4 + (mem & 1) * 2 + rank;
  const int rb2 = (grp >> 2) * 8 + mem, cb2 = (grp & 3) * 2 + rank;
  const int chb = grp * 16 + mem * 2 + rank;
  const int cta = rg * 16 + hp;
  const int par = rg >> 2, gidx = rg & 3;

  if (tid < 256 && !halo_cta && MODE != 2) {
    const int r = tid >> 3, c = tid & 7;
    const uint32_t so = r * 128 + ((c ^ (r & 7)) << 4);
    const __nv_bfloat16* wg0 = p.w + (size_t)r * (3 * DM) + hp * 64 + c * 8;
    const __nv_bfloat16* xg0 = p.x + (size_t)(2 * (gidx * 256 + r) + par) * DM + c * 8;
#pragma unroll
    for (int j = 0; j < 3; j++) cp_async16n(sb + OFF_1B + j * 4096 + so, wg0 + j * DM);
#pragma unroll
    for (int i = 0; i < 8; i++) cp_async16n(sb + i * 4096 + so, xg0 + (size_t)i * 64 * DM);
    asm volatile("cp.async.commit_group;\n" ::: "memory");
  }
  if (tid == 256) {
    prefetch_tmap(halo_cta ? &tmXh : &tmX);
#pragma unroll
    for (int i = 0; i < NS1B; i++) mbar_init(bars + 8 * (BAR_FULLB + i), 1);
#pragma unroll
    for (int i = 0; i < NS1A; i++) mbar_init(bars + 8 * (BAR_FULLA + i), 1);
    asm volatile("fence.mbarrier_init.release.cluster;\n" ::: "memory");
    if (!halo_cta && MODE != 2) {
      mbar_expect_tx(bars + 8 * (BAR_FULLB + 1), STG1B);
      tma_load_3d(sb + OFF_1B + 1 * STG1B, &tmW, bars + 8 * (BAR_FULLB + 1), hp * 64, 32, 0);
      mbar_expect_tx(bars + 8 * (BAR_FULLB + 2), STG1B);
      tma_load_3d(sb + OFF_1B + 2 * STG1B, &tmW, bars + 8 * (BAR_FULLB + 2), hp * 64, 64, 0);
    } else {
      prefetch_tmap(&tmWh);
    }
  } else if (tid == 288) {
#pragma unroll
    for (int i = 0; i < NS1A; i++) mbar_init(bars + 8 * (BAR_EMPTYA + i), 4);
#pragma unroll
    for (int i = 0; i < NS1B; i++) mbar_init(bars + 8 * (BAR_EMPTYB + i), 2);
    asm volatile("fence.mbarrier_init.release.cluster;\n" ::: "memory");
  } else if (tid == 320) {
#pragma unroll
    for (int i = 0; i < NS2; i++) {
      mbar_init(bars + 8 * (BAR_FULL2 + i), 1);
      mbar_init(bars + 8 * (BAR_EMPTY2 + i), 4);
    }
    mbar_init(bars + 8 * BAR_DEAD, 2);
    mbar_init(bars + 8 * (BAR_DEAD + 1), 2);
    mbar_init(bars + 8 * BAR_X, 2);
    mbar_init(bars + 8 * BAR_REL, 2);
    asm volatile("fence.mbarrier_init.release.cluster;\n" ::: "memory");
  } else if (tid == 352) {
    mbar_init(bars + 8 * BAR_T, 1);
    mbar_init(bars + 8 * BAR_UH, 3);
    mbar_init(bars + 8 * BAR_LFREE, 4);
    mbar_init(bars + 8 * BAR_LAND, 1);
    mbar_init(bars + 8 * BAR_U, 1);
    mbar_init(bars + 8 * BAR_Q, 1);
    mbar_init(bars + 8 * BAR_STG, 9);
    asm volatile("fence.mbarrier_init.release.cluster;\n" ::: "memory");
  }
  if (warp == 8) PROF2(23);
  cluster_sync_all();
  if (warp == 8) PROF2(24);

  if (warp >= 8) {
    const int hw = warp - 8;
    const int lr = lane & 7, lm = lane >> 3;
    auto g1_issue_a = [&](int j, int s) {
      const uint32_t fb = bars + 8 * (BAR_FULLA + s);
      mbar_expect_tx(fb, STG1A);
      tma_load_3d_mc(sb + s * STG1A + rank * 16384, &tmX, fb, j * 64, par, gidx * 256 + rank * 128);
    };
    auto g1_issue_b = [&](int kb, int s) {
      const uint32_t fb = bars + 8 * (BAR_FULLB + s);
      mbar_expect_tx(fb, STG1B);
      tma_load_3d(sb + OFF_1B + s * STG1B, &tmW, fb, hp * 64, kb * 32, 0);
    };
    asm volatile("setmaxnreg.dec.sync.aligned.u32 %0;\n" :: "n"(REG_HELP));

    if (halo_cta) {
      if (hw == 0) {
        int s = 0, ph = 1;
#pragma unroll 1
        for (int kb = 0; kb < 16; kb++) {
          mbar_wait(bars + 8 * (BAR_EMPTYB + s), ph);
          const uint32_t fb = bars + 8 * (BAR_FULLB + s), st = sb + s * STGH;
          if (elect_one()) {
            mbar_expect_tx(fb, STGH);
            tma_load_4d(st, &tmXh, fb, kb * 64, 248, 0, 0);
            tma_load_3d(st + 8192, &tmWh, fb, 0, kb * 64, 16 + blockIdx.x * 4);
            tma_load_3d(st + 8192 + 32768, &tmWh, fb, 0, kb * 64, 32 + blockIdx.x * 4);
          }
          if (++s == 3) { s = 0; ph ^= 1; }
        }
      }
      __syncwarp();
    } else if (hw == 0) {
      uint32_t epoch = 0;
      if (lane < (MODE == 2 ? NS2 : 2)) mbar_arrive_cluster_n(mapa(bars, rank) + 8 * (BAR_EMPTY2 + lane), 4);
      if (MODE != 2) {
      epoch = ld_relaxed(g_flag_o + 2 * cta) + 1;
      if (lane == 0) {
        mbar_expect_tx(bars + 8 * BAR_U, 32768);
        mbar_expect_tx(bars + 8 * BAR_LAND, 32768);
        mbar_expect_tx(bars + 8 * BAR_Q, 32768);
        mbar_expect_tx(bars + 8 * BAR_T, T_END);
      }
      {
        int sa = 1, pha = 1, sbb = 2, phb = 1;
#pragma unroll 1
        for (int kb = 2; kb < 32; kb++) {
          if (!(kb & 1)) {
            mbar_wait(bars + 8 * (BAR_EMPTYA + sa), pha);
            if (elect_one()) g1_issue_a(kb >> 1, sa);
            if (++sa == NS1A) { sa = 0; pha ^= 1; }
          }
          mbar_wait(bars + 8 * (BAR_EMPTYB + sbb), phb);
          if (kb > 2 && elect_one()) g1_issue_b(kb, sbb);
          __syncwarp();
          if (kb == 4) PROF2(27);
          if (kb == 1) PROF2(38);
          if (kb == 2) PROF2(39);
          if (++sbb == NS1B) { sbb = 0; phb ^= 1; }
        }
      }
      static_assert(32 % NS1B == 2 && (32 / NS1B) % 2 == 0 && OFF_Q == OFF_1B && 2 * STG1B == 6 * 4096, "slots / parity of these loads");
      const uint8_t* tab = reinterpret_cast<const uint8_t*>(g_tab);
      if (lane == 0) {
        prefetch_tmap(&tmWo);
        prefetch_tmap(&tmQ);
        bulk_load(sb + OFF_T + T_A1, tab + T_A1, T_END - T_A1, bars + 8 * BAR_T);
        mbar_wait(bars + 8 * (BAR_EMPTYB + 2), 1);
        tma_load_5d(sb + OFF_Q + 6 * 4096, &tmQ, bars + 8 * BAR_Q, (chb & ~1) * 8, rank * 32 + 24);
        tma_load_5d(sb + OFF_Q + 7 * 4096, &tmQ, bars + 8 * BAR_Q, (chb & ~1) * 8, rank * 32 + 28);
        if (gidx != 0) wait_flag(g_flag_h + (hp >> 2), epoch);
      }
      __syncwarp();
      {
        uint4 hk0 = make_uint4(0, 0, 0, 0), hk1 = hk0, hv0 = hk0, hv1 = hk0;
        if (gidx != 0) {
          const uint4* src = g_halo + cta * 128 + lane;
          hk0 = __ldcg(src); hk1 = __ldcg(src + 32); hv0 = __ldcg(src + 64); hv1 = __ldcg(src + 96);
        }
        if (lane == 0) {
          mbar_wait(bars + 8 * (BAR_EMPTYB + 3), 1);
          bulk_load(sb + OFF_T, tab, T_TW, bars + 8 * BAR_T);
        }
        __syncwarp();
        PROF2(18);
        sts128(sb + OFF_L0 + 1024 + lane * 16, hk0.x, hk0.y, hk0.z, hk0.w);
        sts128(sb + OFF_L0 + 1536 + lane * 16, hk1.x, hk1.y, hk1.z, hk1.w);
        stsm4(sb + OFF_L0 + lr * 128 + ((lm ^ lr) << 4), hv0.x, hv0.y, hv0.z, hv0.w);
        stsm4(sb + OFF_L0 + lr * 128 + (((4 + lm) ^ lr) << 4), hv1.x, hv1.y, hv1.z, hv1.w);
        __syncwarp();
        if (lane == 0) {
          mbar_arrive(bars + 8 * BAR_STG);
          mbar_wait(bars + 8 * (BAR_EMPTYB + 4), 1);
          bulk_load(sb + OFF_T + T_TW, tab + T_TW, T_A1 - T_TW, bars + 8 * BAR_T);
          mbar_wait(bars + 8 * BAR_EMPTYB, 0);
#pragma unroll 1
          for (int i = 0; i < 6; i++) tma_load_5d(sb + OFF_Q + i * 4096, &tmQ, bars + 8 * BAR_Q, (chb & ~1) * 8, rank * 32 + i * 4);
        }
        __syncwarp();
      }
      }
      if (MODE != 1) {
        auto korder = [&](int i) { return MODE == 2 ? i : i < 2 ? hp ^ 1 ^ i : i < 4 ? (hp & ~1) ^ i : ((hp & ~3) + i) & 15; };
        if (MODE == 0) {
          mbar_wait(bars + 8 * (BAR_EMPTY2 + 2), 0);
          if (elect_one()) {
            mbar_expect_tx(bars + 8 * BAR_FULL2, STG2);
            tma_load_3d(sb + g2_b(0), &tmWo, bars + 8 * BAR_FULL2, 0, korder(0) * 64, cb2 * 2);
            tma_load_3d(sb + g2_b(1), &tmWo, bars + 8 * (BAR_FULL2 + 1), 0, korder(1) * 64, cb2 * 2);
          }
        }
        PROF2(20);
        const __nv_bfloat16* osrc = g_o + (size_t)(rb2 >> 1) * 16 * 16384 + ((rb2 & 1) * 2 + rank) * 4096;
        const uint32_t* flag = g_flag_o + (rb2 >> 1) * 32 + korder(lane & 15) * 2 + (rb2 & 1);
        uint32_t ready = MODE == 0 ? 0u : ~0u;
        int s = MODE == 0 ? 2 : 0, ph = 0;
#pragma unroll 1
        for (int i = s; i < 16; i++) {
          const int kb = korder(i);
          const uint32_t fb = bars + 8 * (BAR_FULL2 + s);
          if (!((ready >> i) & 1)) {
            int n = 0;
            do {
              ready = __ballot_sync(0xffffffffu, ld_acquire(flag) == epoch);
            } while (!((ready >> i) & 1) && ++n < SPIN_LIMIT);
            fence_async_all();
          }
          if (i == 2) PROF(21);
          mbar_wait(bars + 8 * (BAR_EMPTY2 + s), ph);
          if (elect_one()) {
            mbar_expect_tx(fb, STG2);
            asm volatile(
                "cp.async.bulk.shared::cluster.global.mbarrier::complete_tx::bytes.multicast::cluster [%0], [%1], %2, [%3], %4;\n"
                ::"r"(sb + g2_a(s) + rank * 8192), "l"(osrc + kb * 16384), "r"(8192), "r"(fb), "h"((uint16_t)3) : "memory");
            if (MODE != 0 || i >= 4) tma_load_3d(sb + g2_b(s), &tmWo, fb, 0, kb * 64, cb2 * 2);
          }
          if (++s == NS2) { s = 0; ph ^= 1; }
          if (i == 3) PROF(37);
        }
      }
      __syncwarp();
    } else if (MODE != 2) {
      {
        const int g = lane >> 2, t = lane & 3;
        uint32_t w[2][4];
#pragma unroll
        for (int h = 0; h < 2; h++) {
          const uint2 x = __ldg(reinterpret_cast<const uint2*>(p.shift_k + ((chb & ~1) * 8 + h * 8 + g) * 4));
          w[h][0] = __byte_perm(x.x, x.x, 0x1010);
          w[h][1] = __byte_perm(x.x, x.x, 0x3232);
          w[h][2] = __byte_perm(x.y, x.y, 0x1010);
          w[h][3] = __byte_perm(x.y, x.y, 0x3232);
        }
        auto swz = [](int r) { return (((r & 29) | ((r ^ (r >> 2)) & 2)) << 5) | (r & 16); };
        const uint32_t kring = sb + OFF_H + (hw - 1) * 8192, vring = kring + 4096;
        const int s0 = rank * 32 + (hw - 1) * 11, s1 = hw == 3 ? rank * 32 + 32 : s0 + 11;
        const size_t goff = (size_t)(lane >> 1) * DM + (chb & ~1) * 8 + (lane & 1) * 8;
        const __nv_bfloat16* kg = p.k + goff;
        const __nv_bfloat16* vg = p.v + goff;
        const uint32_t d0 = swz(lane >> 1) ^ ((lane & 1) << 4), d1 = swz(16 + (lane >> 1)) ^ ((lane & 1) << 4);
        auto issue = [&](int st) {
          const uint32_t so = (st & 3) << 10;
          cp_async16(kring + so + d0, kg + (size_t)st * 32 * DM, 16);
          cp_async16(kring + so + d1, kg + (size_t)(st * 32 + 16) * DM, 16);
          cp_async16(vring + so + d0, vg + (size_t)st * 32 * DM, 16);
          cp_async16(vring + so + d1, vg + (size_t)(st * 32 + 16) * DM, 16);
        };
        const int xa = 8 * (lr >> 1) + 2 * lm + (lr & 1), xb = 8 * (lr >> 1) - 4 + 2 * (lm & 1) + (lr & 1);
        const uint32_t la = swz(xa), lb = swz(xb & 31);
        const int backb = xb < 0 ? 1 : 0;
        const uint32_t ud[2] = {mapa(sb + OFF_U + g * 4096 + t * 16, 0), mapa(sb + OFF_U + g * 4096 + t * 16, 1)};
        const uint32_t ub[2] = {mapa(bars + 8 * BAR_U, 0), mapa(bars + 8 * BAR_U, 1)};
        if (lane == 0) mbar_wait(bars + 8 * (BAR_FULLB + NS1B - 1), 0);
        __syncwarp();
        if (lane >= 24) cp_async16(kring + (((s0 - 1) & 3) << 10) + d1, s0 > 0 ? kg + (size_t)(s0 * 32 - 16) * DM : kg, s0 > 0 ? 16 : 0);
        issue(s0);
        asm volatile("cp.async.commit_group;\n" ::: "memory");
        issue(s0 + 1);
        asm volatile("cp.async.commit_group;\n" ::: "memory");
#pragma unroll 1
        for (int st = s0; st < s1; st++) {
          if (st + 2 < s1) issue(st + 2);
          if (hw == 1 && st - s0 < 8) prefetch_l2(p.ssm_k + (size_t)(chb * 8 + st - s0) * SEQ + lane * 64);
          if (hw == 2 && st == s0 + 4 && lane < 2) prefetch_l2(g_tab + (chb * 2 + lane) * 32);
          const uint32_t uo = (st ^ ((g ^ (st >> 2)) & 1)) * 64;
          asm volatile("cp.async.commit_group;\n" ::: "memory");
          asm volatile("cp.async.wait_group 2;\n" ::: "memory");
          __syncwarp();
#pragma unroll
          for (int h = 0; h < 2; h++) {
            uint32_t e[6], vv[4], e4[4];
            ldsm4t(e4, kring + ((st & 3) << 10) + (la ^ (h << 4)));
            ldsm2t(e[0], e[1], kring + (((st - backb) & 3) << 10) + (lb ^ (h << 4)));
            ldsm4t(vv, vring + ((st & 3) << 10) + (la ^ (h << 4)));
            e[2] = e4[0]; e[3] = e4[1]; e[4] = e4[2]; e[5] = e4[3];
            uint32_t o[5];
#pragma unroll
            for (int i = 0; i < 5; i++) o[i] = __byte_perm(e[i], e[i + 1], 0x5432);
#pragma unroll
            for (int i = 0; i < 4; i++) {
              uint32_t a = bmul2(o[i], w[h][3]);
              a = bfma2(e[i + 1], w[h][2], a);
              a = bfma2(o[i + 1], w[h][1], a);
              a = bfma2(e[i + 2], w[h][0], a);
              vv[i] = bmul2(a, vv[i]);
            }
            st_async128(ud[h] + uo, ub[h], vv[0], vv[1], vv[2], vv[3]);
          }
          __syncwarp();
        }
        PROF(16);
      }
      {
        const int rw = (lane >> 3) + (lane & 4), ck = lane & 3;
        const uint32_t so = rw * 64 + ck * 16, dof = rw * 128 + ((ck ^ rw) << 4);
        const uint8_t* hsrc = reinterpret_cast<const uint8_t*>(p.ssm_k + (size_t)chb * 8 * SEQ) + so;
        const float dv = lane < 8 ? __bfloat162float(p.ssm_D[chb * 8 + lane]) : 0.f;
        uint32_t x[32];
        auto load = [&](const uint8_t* src, int i) {
          asm volatile("ld.v4.u32 {%0,%1,%2,%3}, [%4];\n" : "=r"(x[4 * i]), "=r"(x[4 * i + 1]), "=r"(x[4 * i + 2]), "=r"(x[4 * i + 3])
                       : "l"(src + i * 512) : "memory");
        };
#pragma unroll
        for (int i = 0; i < 8; i++) load(hsrc + (hw - 1) * 4096, i);
        nb_sync(NB_HELP3, 96);
        mbar_wait(bars + 8 * BAR_U, 0);
        int eh = 0;
#pragma unroll 1
        for (int n = 2 * (hw - 1); n < 16; n += (n & 1) ? 5 : 1) {
          const int c = n >> 1;
          const uint8_t* nsrc = (n & 1) ? hsrc + (c < 5 ? c + 3 : c) * 4096
                                        : smem + OFF_U + c * 4096 + (so ^ (((c ^ (lane >> 2)) & 1) << 6));
          const uint32_t dst = sb + ((n & 1) ? OFF_U : OFF_H) + c * 4096 + dof;
          const float dc = __shfl_sync(0xffffffffu, dv, c);
          const float h0 = bf_lo(x[0]) + ((lane | (n & 1)) == 0 ? dc : 0.f), h1 = bf_hi(x[0]);
          x[0] = pack_bf16(h0, h1);
          uint32_t m[2] = {x[0], x[1]};
#pragma unroll
          for (int i = 2; i < 32; i++) asm("max.xorsign.abs.bf16x2 %0, %0, %1;\n" : "+r"(m[i & 1]) : "r"(x[i]));
          asm("max.xorsign.abs.bf16x2 %0, %0, %1;\n" : "+r"(m[0]) : "r"(m[1]));
          const uint32_t e = max(__reduce_max_sync(0xffffffffu, max((m[0] >> 7) & 255u, (m[0] >> 23) & 255u)), 5u);
          const uint32_t sc = (259u - e) * 0x00800080u;
#pragma unroll
          for (int i = 0; i < 8; i++) {
            uint32_t o[4];
#pragma unroll
            for (int j = 0; j < 4; j++) {
              const uint32_t v = bmul2(x[4 * i + j], sc);
              asm("cvt.rn.f16x2.f32 %0, %1, %2;\n" : "=r"(o[j]) : "f"(bf_hi(v)), "f"(i + j == 0 ? h0 * bf_hi(sc) : bf_lo(v)));
            }
            sts128((dst + (i & 3) * 1024) ^ ((i >> 2) << 6), o[0], o[1], o[2], o[3]);
            load(nsrc, i);
          }
          if (n & 1) {
            const int f = min(max((int)e + eh - 129, 0), 254);
            if (lane == 0) asm volatile("st.shared.u32 [%0], %1;\n" ::"r"(sb + OFF_SC + c * 4), "r"(f << 23) : "memory");
            prefetch_l2(p.q + (size_t)chb * 16384 + c * 2048 + lane * 64);
            if (lane < 16) prefetch_l2(p.wo + (size_t)chb * 8192 + c * 1024 + lane * 64);
          }
          eh = e;
        }
        fence_async_smem();
        __syncwarp();
        if (lane == 0) mbar_arrive(bars + 8 * BAR_UH);
        PROF(32);
      }
      if (hw < 3) {
        const uint32_t rb = mapa(bars, lane & 1);
        const uint32_t epoch = ld_relaxed(g_flag_o + 2 * cta + hw - 1) + 1;
        const bool own = hw - 1 == (rb2 & 1);
        nb_sync(NB_OREADY + hw - 1, 160);
        if (lane == 0) {
          asm volatile("cp.async.bulk.global.shared::cta.bulk_group [%0], [%1], %2;\n" ::"l"(g_o + (size_t)cta * 16384 + (hw - 1) * 8192),
                       "r"(sb + OFF_OP + (own ? 16384 : 0)), "r"(16384) : "memory");
          bulk_commit();
        }
        if (lane < 2) {
          mbar_arrive_cluster(rb + 8 * (BAR_EMPTY2 + 2));
          mbar_arrive_cluster(rb + 8 * (BAR_EMPTY2 + 3));
        }
        if (lane == 0) {
          asm volatile("cp.async.bulk.wait_group.read 0;\n" ::: "memory");
          if (own) mbar_expect_tx(bars + 8 * (BAR_FULL2 + 1), 16384);
          mbar_arrive_cluster(mapa(bars, own ? rank : rank ^ 1) + 8 * BAR_X);
        }
        PROF2(19);
        if (lane == 0) {
          bulk_wait0();
          st_release(g_flag_o + 2 * cta + hw - 1, epoch);
          mbar_arrive(bars + 8 * BAR_REL);
        }
        __syncwarp();
        PROF(17);
      } else {
        mbar_wait(bars + 8 * BAR_REL, 0);
        if (MODE == 0) {
          mbar_wait(bars + 8 * BAR_X, 0);
          if (elect_one())
            asm volatile("cp.async.bulk.shared::cluster.shared::cta.mbarrier::complete_tx::bytes [%0], [%1], %2, [%3];\n"
                         ::"r"(mapa(sb + OFF_OP, rank ^ 1)), "r"(sb + OFF_OP + 16384), "r"(16384),
                         "r"(mapa(bars + 8 * BAR_FULL2, rank ^ 1)) : "memory");
        }
        if (MODE == 0) {
          mbar_wait(bars + 8 * BAR_DEAD, 0);
          if (elect_one()) {
            tma_load_3d(sb + g2_b(2), &tmWo, bars + 8 * (BAR_FULL2 + 2), 0, ((hp & ~1) ^ 2) * 64, cb2 * 2);
            tma_load_3d(sb + g2_b(3), &tmWo, bars + 8 * (BAR_FULL2 + 3), 0, ((hp & ~1) ^ 3) * 64, cb2 * 2);
          }
        }
        __syncwarp();
      }
      {
        const int c8 = (4 * (lr >> 1) + 2 * (lm & 1) + (lr & 1)) & 7;
        const bool own = (lr >> 2) == rank;
        const uint32_t ya = sb + (own ? y_slot(c8 & 1, c8 >> 1) : OFF_LAND + c8 * 2048);
        const uint32_t yx = ((lm >> 1) ^ lr) << 4;
        const int row = (lane >> 3) * 8 + ((lane >> 2) & 1);
        uint2* og = reinterpret_cast<uint2*>(p.out + (size_t)(rank * 1024 + row) * (2 * DM) + (chb & ~1) * 8 + (lane & 3) * 4);
        const uint32_t qa = sb + OFF_Q + lane * 8;
        mbar_wait(bars + 8 * BAR_Q, 0);
        mbar_wait(bars + 8 * BAR_LAND, 0);
        PROF(33);
        const uint32_t t0 = clock();
#pragma unroll 1
        for (int j = hw - 1; j < 16; j += 3) {
          uint32_t y[4][4];
          uint2 q[8];
          while ((uint32_t)clock() - t0 < j * PACE) __nanosleep(40);
          const uint32_t qj = qa + j * 2048;
#pragma unroll
          for (int i = 0; i < 4; i++) ldsm4t(y[i], ya + j * 128 + (yx ^ (i << 5)));
#pragma unroll
          for (int i = 0; i < 8; i++) q[i] = lds64(qj + i * 256);
#pragma unroll
          for (int i = 0; i < 8; i++)
            og[(size_t)(j * 64 + (i >> 2) * 32 + (i & 3) * 2) * (2 * DM / 4)] =
                make_uint2(bmul2(q[i].x, y[i >> 1][2 * (i & 1)]), bmul2(q[i].y, y[i >> 1][2 * (i & 1) + 1]));
        }
      }
      PROF(22);
    }
    cluster_sync_all();
  } else {
    asm volatile("setmaxnreg.inc.sync.aligned.u32 %0;\n" :: "n"(REG_MATH));
    if (warp == 0) PROF2(26);
    const int wg = warp >> 2;
    const int wtid = tid & 127;
    const bool signaller = (wtid == 0) || (wtid == 32);
    const uint32_t rbars = mapa(bars, wtid >> 5 & 1);

    if (halo_cta) {
      const uint32_t epoch = ld_relaxed(g_flag_h + blockIdx.x) + 1;
      float acc0[64], acc1[64];
      int s = 0, ph = 0;
#pragma unroll 1
      for (int kb = 0; kb < 16; kb++) {
        mbar_wait(bars + 8 * (BAR_FULLB + s), ph);
        const uint32_t st = sb + s * STGH;
        const uint64_t da = mkdesc(st, 16, 1024, 1);
        const uint64_t db = mkdesc(st + 8192 + wg * 32768, 8192, 1024, 1);
        wg_fence();
#pragma unroll
        for (int kk = 0; kk < 4; kk++) {
          wgmma_n128(acc0, da + 2 * kk, db + 128 * kk, kb + kk);
          wgmma_n128(acc1, da + 2 * kk, db + 1024 + 128 * kk, kb + kk);
        }
        wg_commit();
        wg_wait<0>();
        if (wtid == 0) mbar_arrive(bars + 8 * (BAR_EMPTYB + s));
        if (++s == 3) { s = 0; ph ^= 1; }
      }
      fence_regs(acc0);
      fence_regs(acc1);
      if ((warp & 3) != 3) {
#pragma unroll
        for (int hh = 0; hh < 2; hh++) {
          uint4* dst = g_halo + ((hh * 4 + (warp & 3) + 1) * 16 + blockIdx.x * 4) * 128 + wg * 64 + lane;
#pragma unroll
          for (int j = 0; j < 4; j++) {
            const int o = 16 * j + 2 * hh;
            dst[(j >> 1) * 128 + (j & 1) * 32] =
                make_uint4(pack_bf16(acc0[o], acc0[o + 1]), pack_bf16(acc0[o + 4], acc0[o + 5]),
                           pack_bf16(acc0[o + 8], acc0[o + 9]), pack_bf16(acc0[o + 12], acc0[o + 13]));
            dst[(2 + (j >> 1)) * 128 + (j & 1) * 32] =
                make_uint4(pack_bf16(acc1[o], acc1[o + 1]), pack_bf16(acc1[o + 4], acc1[o + 5]),
                           pack_bf16(acc1[o + 8], acc1[o + 9]), pack_bf16(acc1[o + 12], acc1[o + 13]));
          }
        }
      }
      nb_sync(NB_G1DONE, 256);
      if (tid == 0) st_release(g_flag_h + blockIdx.x, epoch);
      PROF(36);
      cluster_sync_all();
      return;
    }

    if (MODE != 2) {
    {
      float acc0[96], acc1[96];
      int sa = 0, pha = 0, sbb = 0, phb = 0;
      asm volatile("cp.async.wait_group 0;\n" ::: "memory");
      fence_async_smem();
      nb_sync(NB_FIRST, 256);
      if (tid == 0) {
        mbar_arrive(bars + 8 * BAR_FULLA);
        mbar_arrive(bars + 8 * BAR_FULLB);
      }
      PROF(0 + wg);
#pragma unroll 1
      for (int kb = 0; kb < 30; kb++) {
        if (!(kb & 1)) mbar_wait(bars + 8 * (BAR_FULLA + sa), pha);
        mbar_wait(bars + 8 * (BAR_FULLB + sbb), phb);
        if (kb == 0) PROF2(0 + wg);
        if (kb == 4 && wg == 0) PROF2(28);
        if (kb == 8 && wg == 0) PROF2(29);
        if (kb == 16 && wg == 0) PROF2(30);
        const uint64_t da = mkdesc(sb + sa * STG1A + wg * 16384 + (kb & 1) * 64, 16, 1024, 1);
        const uint64_t db = mkdesc(sb + OFF_1B + sbb * STG1B, 4096, 1024, 1);
        wg_fence();
        wgmma_n192(acc0, da, db, kb);
        wgmma_n192(acc1, da + 512, db, kb);
        wgmma_n192(acc0, da + 2, db + 128, 1);
        wgmma_n192(acc1, da + 514, db + 128, 1);
        wg_commit();
        wg_wait<1>();
        if (kb > 0) {
          if (wtid == 64) mbar_arrive(bars + 8 * (BAR_EMPTYB + (sbb == 0 ? NS1B - 1 : sbb - 1)));
          if (!(kb & 1) && signaller) mbar_arrive_cluster(rbars + 8 * (BAR_EMPTYA + (sa == 0 ? NS1A - 1 : sa - 1)));
        }
        if (++sbb == NS1B) { sbb = 0; phb ^= 1; }
        if ((kb & 1) && ++sa == NS1A) { sa = 0; pha ^= 1; }
      }
      const int blk0 = wg * 8 + (warp & 3);
      const int lr = lane & 7, lm = lane >> 3;
      const bool le0 = 2 * (lane & 3) <= (lane >> 2), le1 = 2 * (lane & 3) + 1 <= (lane >> 2);
      const uint32_t maskLE = (le0 ? 0x0000FFFFu : 0u) | (le1 ? 0xFFFF0000u : 0u);
      uint32_t k0[2][2][4], k1[2][2][4], qa[2][2][8];
      float l[2][2][4];
      {
        static_assert(15 % NS1A == 0 && 30 % NS1B == 0, "slots of the last k blocks");
        mbar_wait(bars + 8 * BAR_FULLA, 1);
        mbar_wait(bars + 8 * BAR_FULLB, 0);
        mbar_wait(bars + 8 * (BAR_FULLB + 1), 0);
        const uint64_t da = mkdesc(sb + wg * 16384, 16, 1024, 1);
        const uint64_t db = mkdesc(sb + OFF_1B, 4096, 1024, 1);
        wg_fence();
#pragma unroll
        for (int i = 0; i < 4; i++) wgmma_n192(acc0, da + 2 * i, db + (i >> 1) * (STG1B >> 4) + (i & 1) * 128, 1);
        wg_commit();
        wg_wait<1>();
        if (wtid == 64) mbar_arrive(bars + 8 * (BAR_EMPTYB + NS1B - 1));
#pragma unroll
        for (int i = 0; i < 2; i++) wgmma_n192(acc1, da + 512 + 2 * i, db + (i >> 1) * (STG1B >> 4) + (i & 1) * 128, 1);
        wg_commit();
        wg_wait<1>();
        fence_regs(acc0);
        attn_stage(sb, blk0, lane, acc0, k1[0]);
#pragma unroll
        for (int i = 2; i < 4; i++) wgmma_n192(acc1, da + 512 + 2 * i, db + (i >> 1) * (STG1B >> 4) + (i & 1) * 128, 1);
        wg_commit();
        attn_pack(acc0, qa[0], k0[0]);
        wg_wait<0>();
        fence_regs(acc1);
      }
      if (wtid == 64) mbar_arrive(bars + 8 * BAR_EMPTYB);
      PROF(2 + wg);
      attn_stage(sb, blk0 + 4, lane, acc1, k1[1]);
      __syncwarp();
      if (lane == 0) mbar_arrive(bars + 8 * BAR_STG);
      mbar_wait(bars + 8 * BAR_U, 0);
      attn_pack(acc1, qa[1], k0[1]);
      attn_own(k0[0], k1[0], le0, le1, qa[0], l[0]);
      attn_own(k0[1], k1[1], le0, le1, qa[1], l[1]);
      const uint32_t cho[2] = {(uint32_t)(((lm & 1) ^ lr) << 4), (uint32_t)(((2 + (lm & 1)) ^ lr) << 4)};
      const uint32_t obase = sb + OFF_OP + (wg == (rb2 & 1) ? 16384 : 0) + ((warp & 3) * 16 + lr) * 128;
      mbar_wait(bars + 8 * BAR_STG, 0);
      {
        uint32_t km[4][4], va[8][4], vb[8][4], pp[8];
        float x[8][2];
#pragma unroll
        for (int n = 0; n < 4; n++) {
          const int blk = blk0 + 4 * (n >> 1);
          to_arr(km[n], lds128(sb + (blk == 0 ? OFF_L0 + 1024 : OFF_KH + (blk - 1) * 2048) + (n & 1) * 512 + lane * 16));
        }
#pragma unroll
        for (int n = 0; n < 8; n++) {
          const int vr = (blk0 + 4 * ((n >> 1) & 1)) * 16 - 8 + 8 * (n >> 2) + 8 * (lm >> 1);
          const uint32_t vrow = sb + (vr < 0 ? OFF_L0 : OFF_VP + vr * 128) + lr * 128;
          ldsm4t(va[n], vrow + (cho[0] ^ ((n & 1) << 6)));
          ldsm4t(vb[n], vrow + (cho[1] ^ ((n & 1) << 6)));
        }
        const bool first = blk0 == 0 && gidx == 0;
#pragma unroll
        for (int n = 0; n < 4; n++) {
          const uint32_t(&q)[8] = qa[n >> 1][n & 1];
          float sm[4];
          mma16816_z(sm, q[0], q[1], q[2], q[3], km[n][0], km[n][1]);
          mma16816(sm, q[4], q[5], q[6], q[7], km[n][2], km[n][3]);
          if (n < 2 && first) sm[0] = sm[1] = -1e9f / 0.17677669529663687f;
          x[n][0] = le0 ? l[n >> 1][n & 1][0] : sm[0];
          x[n][1] = le1 ? l[n >> 1][n & 1][1] : sm[1];
          x[4 + n][0] = l[n >> 1][n & 1][2];
          x[4 + n][1] = l[n >> 1][n & 1][3];
        }
        quad_softmax<8>(x, pp);
#pragma unroll
        for (int n = 7; n >= 0; n--)
          attn_pv(obase + ((n >> 1) & 1) * 8192 + (n >> 2) * 1024 + (((4 * (n & 1) + lm) ^ lr) << 4), va[n], vb[n], pp[n],
                  maskLE);
      }
      fence_async_smem();
      nb_arrive(NB_OREADY + wg, 160);
    }

    {
      const int w = warp & 3;
      uint32_t a1[2][4], a4[8][4], tw[16], d1[32];
      float d4[16];
      const uint32_t tb = sb + OFF_T + wtid * 16;
      PROF(34 + wg);
      mbar_wait(bars + 8 * BAR_T, 0);
      mbar_wait(bars + 8 * BAR_UH, 0);
      to_arr(a1[0], lds128(tb + T_A1));
      to_arr(a1[1], lds128(tb + T_A1 + 2048));
      const uint64_t dx = mkdesc(sb + OFF_U + wg * 4096, OFF_H - OFF_U, 1024, 1);
      const uint64_t dz = mkdesc(sb + OFF_U + wg * 4096, 512, 128, 0);
      const uint64_t db2 = mkdesc(sb + OFF_T + T_B2, 128, 256, 0);
      wg_fence();
      hmma_n128t<0>(d1, a1[0], dx);
      hmma_n128t<1>(d1, a1[1], dx + 128);
      wg_commit();
      auto ldtw = [&](int i) {
        const uint4 v = lds128(tb + T_TW + i * 2048);
        tw[4 * i] = v.x; tw[4 * i + 1] = v.y; tw[4 * i + 2] = v.z; tw[4 * i + 3] = v.w;
      };
      ldtw(0);
      ldtw(1);
      const uint32_t za = sb + (w < 2 ? OFF_U : OFF_H) + wg * 4096 + (w & 1) * 2048 + lane * 16;
      const uint32_t yl = (wtid ^ (4 * rank + wg)) * 16;
      const uint32_t yown = mapa(sb, rank) + yl, yrem = mapa(sb + OFF_LAND + wg * 2048, rank ^ 1) + yl;
      const uint32_t yb[2] = {mapa(bars + 8 * BAR_LAND, 0), mapa(bars + 8 * BAR_LAND, 1)};
      wg_wait<0>();
      fence_regs(d1);
      nb_sync(NB_WG + wg, 128);
      auto s4 = [&](int it) {
        wg_fence();
#pragma unroll
        for (int ks = 0; ks < 8; ks++) {
          const uint64_t d = dz + (it & 1) * 512 + (ks & 3) * 64 + (ks >> 2) * ((OFF_H - OFF_U) >> 4);
          if (ks == 0) fmma_n32t<0>(d4, a4[ks], d);
          else fmma_n32t<1>(d4, a4[ks], d);
        }
        wg_commit();
      };
      auto e4 = [&](int it) {
        fence_regs(d4);
        const float sc = __uint_as_float(lds32(sb + OFF_SC + wg * 4 + it * 8));
        uint32_t r[8];
#pragma unroll
        for (int i = 0; i < 8; i++) r[i] = pack_bf16(d4[2 * i] * sc, d4[2 * i + 1] * sc);
        const uint32_t o = (yown + y_slot(wg, it)) ^ ((it >> 1) << 5), m = (yrem + it * 4096) ^ ((it >> 1) << 5);
        if (it == 0) mbar_wait(bars + 8 * BAR_LFREE, 0);
        if (it == 3) mbar_wait(bars + 8 * (BAR_DEAD + 1), 0);
        st_async128(rank ? m : o, yb[0], r[0], r[2], r[1], r[3]);
        st_async128(rank ? o : m, yb[1], r[4], r[6], r[5], r[7]);
      };
      uint32_t a2[2][2][2][4], a3[2][2][4], d2[2][2][8], d3[2][8];
      auto s2a = [&]() {
        wg_fence();
#pragma unroll
        for (int c = 0; c < 4; c++) hmma_n32<0, 0>(d2[c & 1][c >> 1], a2[0][c & 1][c >> 1], db2 + (c >> 1) * 128);
      };
      auto s2b = [&]() {
        wg_fence();
#pragma unroll
        for (int c = 0; c < 4; c++) {
          hmma_n32<1, 0>(d2[c & 1][c >> 1], a2[1][c & 1][c >> 1], db2 + (c >> 1) * 128 + 64);
          if (c & 1) wg_commit();
        }
      };
      auto s1 = [&](int it) {
        hmma_n128t<0>(d1, a1[0], dx + it * 512);
        hmma_n128t<1>(d1, a1[1], dx + it * 512 + 128);
        wg_commit();
      };
      auto done = [&](int it) {
        if (it == 0) {
          if (signaller) mbar_arrive_cluster(rbars + 8 * BAR_LFREE);
        } else if (it >= 2 && wtid == 64) {
          mbar_arrive(bars + 8 * (BAR_DEAD + it - 2));
        }
        if (w == 0) PROF3(40 + 4 * wg + it);
      };
      fft_e1<0>(d1, tw, a2[0]);
      s2a();
      fft_e1<1>(d1, tw, a2[1]);
      s2b();
      s1(1);
      ldtw(2);
      ldtw(3);
#pragma unroll
      for (int i = 0; i < 8; i++) to_arr(a4[i], lds128(tb + T_A4 + i * 2048));
#pragma unroll
      for (int it = 0; it < 4; it++) {
        if (it == 0 || it == 3) wg_wait<2>(); else wg_wait<3>();
        fence_regs(d2[0][0]);
        fence_regs(d2[1][0]);
        fft_e2<0, 0>(d2[0][0], d2[1][0], a3[0]);
        fft_e2<0, 1>(d2[0][0], d2[1][0], a3[1]);
        if (it == 0 || it == 3) wg_wait<1>(); else wg_wait<2>();
        fence_regs(d2[0][1]);
        fence_regs(d2[1][1]);
        fft_e2<1, 0>(d2[0][1], d2[1][1], a3[0]);
        fft_e2<1, 1>(d2[0][1], d2[1][1], a3[1]);
        wg_fence();
        hmma_n32<0, 0>(d3[0], a3[0][0], db2);
        hmma_n32<0, 0>(d3[1], a3[0][1], db2);
        hmma_n32<1, 0>(d3[0], a3[1][0], db2 + 64);
        hmma_n32<1, 0>(d3[1], a3[1][1], db2 + 64);
        wg_commit();
        wg_wait<1>();
        if (it > 0) e4(it - 1);
        if (it < 3) {
          fence_regs(d1);
          fft_e1<0>(d1, tw, a2[0]);
        }
        wg_wait<0>();
        fence_regs(d3[0]);
        fence_regs(d3[1]);
        if (it < 3) s2a();
        fft_e3(d3, tw, za + (it & 1) * 8192);
        if (it < 3) {
          fft_e1<1>(d1, tw, a2[1]);
          s2b();
        }
        fence_async_smem();
        nb_sync(NB_WG + wg, 128);
        done(it);
        s4(it);
        if (it < 2) s1(it + 2);
      }
      wg_wait<0>();
      if (signaller) mbar_arrive_cluster(rbars + 8 * (BAR_EMPTY2 + 4));
      e4(3);
      PROF(6 + wg);
    }
    }

    if (MODE != 1) {
      float acc[64];
      int s = 0, ph = 0;
#pragma unroll 1
      for (int kb = 0; kb < 16; kb++) {
        mbar_wait(bars + 8 * (BAR_FULL2 + s), ph);
        if (kb == 0) PROF(8 + wg);
        if (warp == 4) PROF2(40 + kb);
        const uint64_t da = mkdesc(sb + g2_a(s) + wg * 8192, 16, 1024, 1);
        const uint64_t db = mkdesc(sb + g2_b(s), 8192, 1024, 1);
        wg_fence();
        wgmma_n128(acc, da, db, kb);
        wgmma_n128(acc, da + 2, db + 128, 1);
        wgmma_n128(acc, da + 4, db + 256, 1);
        wgmma_n128(acc, da + 6, db + 384, 1);
        wg_commit();
        wg_wait<0>();
        if (kb < 16 - NS2 && signaller) mbar_arrive_cluster(rbars + 8 * (BAR_EMPTY2 + s));
        if (++s == NS2) { s = 0; ph ^= 1; }
      }
      wg_wait<0>();
      fence_regs(acc);
      PROF(10 + wg);
      const int lr = lane & 7, lm = lane >> 3;
      const uint32_t wbase = sb + warp * 2048;
      const uint32_t base = wbase + (lr + 8 * (lm & 1)) * 128;
#pragma unroll
      for (int j = 0; j < 16; j += 2) {
        const uint32_t a = base + (j >> 3) * 16384 + ((((j & 7) + (lm >> 1)) ^ lr) << 4);
        stsm4(a, pack_bf16(acc[4 * j], acc[4 * j + 1]), pack_bf16(acc[4 * j + 2], acc[4 * j + 3]),
              pack_bf16(acc[4 * j + 4], acc[4 * j + 5]), pack_bf16(acc[4 * j + 6], acc[4 * j + 7]));
      }
      __syncwarp();
      {
        const int rr = lane >> 4, ck = lane & 7, hf = (lane >> 3) & 1;
        uint4* og = reinterpret_cast<uint4*>(p.out + (size_t)(2 * ((rb2 & 7) * 128 + warp * 16 + rr) + (rb2 >> 3)) * (2 * DM) + DM + cb2 * 128 + hf * 64 + ck * 8);
        uint4 v[8];
#pragma unroll
        for (int i = 0; i < 8; i++) v[i] = lds128(wbase + hf * 16384 + (2 * i + rr) * 128 + ((ck ^ ((2 * i + rr) & 7)) << 4));
#pragma unroll
        for (int i = 0; i < 8; i++) og[(size_t)i * 4 * (2 * DM / 8)] = v[i];
      }
      PROF(12 + wg);
    }
    cluster_sync_all();
  }
}

typedef CUresult (*EncodeFn)(CUtensorMap*, CUtensorMapDataType, cuuint32_t, void*, const cuuint64_t*, const cuuint64_t*,
                             const cuuint32_t*, const cuuint32_t*, CUtensorMapInterleave, CUtensorMapSwizzle,
                             CUtensorMapL2promotion, CUtensorMapFloatOOBfill);

void make_map(EncodeFn enc, CUtensorMap* tm, const void* base, int rank, const cuuint64_t* dims, const cuuint64_t* strides,
              const cuuint32_t* box, CUtensorMapSwizzle swz) {
  cuuint32_t es[5] = {1, 1, 1, 1, 1};
  enc(tm, CU_TENSOR_MAP_DATA_TYPE_BFLOAT16, rank, const_cast<void*>(base), dims, strides, box, es,
      CU_TENSOR_MAP_INTERLEAVE_NONE, swz, CU_TENSOR_MAP_L2_PROMOTION_L2_256B, CU_TENSOR_MAP_FLOAT_OOB_FILL_NONE);
}

}

extern "C" void kernel_launch(void* const* d_in, const int* in_sizes, int n_in, void* d_out, int out_size) {
  static EncodeFn enc = nullptr;
  static bool coresident = true;
  if (!enc) {
    void* fn = nullptr;
    cudaDriverEntryPointQueryResult qr;
    cudaGetDriverEntryPoint("cuTensorMapEncodeTiled", &fn, cudaEnableDefault, &qr);
    enc = (EncodeFn)fn;
    cudaFuncSetAttribute(fused_kernel<0>, cudaFuncAttributeMaxDynamicSharedMemorySize, SMEM_BYTES);
    cudaFuncSetAttribute(fused_kernel<1>, cudaFuncAttributeMaxDynamicSharedMemorySize, SMEM_BYTES);
    cudaFuncSetAttribute(fused_kernel<2>, cudaFuncAttributeMaxDynamicSharedMemorySize, SMEM_BYTES);
    cudaLaunchConfig_t cfg = {};
    cfg.gridDim = dim3(NCTA);
    cfg.blockDim = dim3(NTHREADS);
    cfg.dynamicSmemBytes = SMEM_BYTES;
    cudaLaunchAttribute at;
    at.id = cudaLaunchAttributeClusterDimension;
    at.val.clusterDim.x = 2;
    at.val.clusterDim.y = 1;
    at.val.clusterDim.z = 1;
    cfg.attrs = &at;
    cfg.numAttrs = 1;
    int nclusters = 0;
    if (cudaOccupancyMaxActiveClusters(&nclusters, fused_kernel<0>, &cfg) == cudaSuccess) coresident = nclusters >= NCTA / 2;
    (void)cudaGetLastError();
  }
  CUtensorMap tmX, tmW, tmWo, tmQ, tmXh, tmWh;
  {
    cuuint64_t dims[3] = {1024, 2, 1024};
    cuuint64_t str[2] = {2048, 4096};
    cuuint32_t box[3] = {64, 1, 128};
    make_map(enc, &tmX, d_in[6], 3, dims, str, box, CU_TENSOR_MAP_SWIZZLE_128B);
  }
  {
    cuuint64_t dims[3] = {1024, 1024, 3};
    cuuint64_t str[2] = {6144, 2048};
    cuuint32_t box[3] = {64, 32, 3};
    make_map(enc, &tmW, d_in[7], 3, dims, str, box, CU_TENSOR_MAP_SWIZZLE_128B);
  }
  {
    cuuint64_t dims[3] = {64, 1024, 16};
    cuuint64_t str[2] = {2048, 128};
    cuuint32_t box[3] = {64, 64, 2};
    make_map(enc, &tmWo, d_in[8], 3, dims, str, box, CU_TENSOR_MAP_SWIZZLE_128B);
  }
  {
    cuuint64_t dims[5] = {1024, 2, 4, 4, 64};
    cuuint64_t str[4] = {2048, 8 * 2048, 2 * 2048, 32 * 2048};
    cuuint32_t box[5] = {16, 2, 4, 4, 4};
    make_map(enc, &tmQ, d_in[0], 5, dims, str, box, CU_TENSOR_MAP_SWIZZLE_NONE);
  }
  {
    cuuint64_t dims[4] = {1024, 256, 2, 4};
    cuuint64_t str[3] = {4096, 2048, 256 * 4096};
    cuuint32_t box[4] = {64, 8, 2, 4};
    make_map(enc, &tmXh, d_in[6], 4, dims, str, box, CU_TENSOR_MAP_SWIZZLE_128B);
  }
  {
    cuuint64_t dims[3] = {64, 1024, 48};
    cuuint64_t str[2] = {6144, 128};
    cuuint32_t box[3] = {64, 64, 4};
    make_map(enc, &tmWh, d_in[7], 3, dims, str, box, CU_TENSOR_MAP_SWIZZLE_128B);
  }
  Params p;
  p.q = (const __nv_bfloat16*)d_in[0];
  p.k = (const __nv_bfloat16*)d_in[1];
  p.v = (const __nv_bfloat16*)d_in[2];
  p.shift_k = (const __nv_bfloat16*)d_in[3];
  p.ssm_k = (const __nv_bfloat16*)d_in[4];
  p.ssm_D = (const __nv_bfloat16*)d_in[5];
  p.x = (const __nv_bfloat16*)d_in[6];
  p.w = (const __nv_bfloat16*)d_in[7];
  p.wo = (const __nv_bfloat16*)d_in[8];
  p.out = (__nv_bfloat16*)d_out;
  if (coresident) {
    fused_kernel<0><<<NCTA, NTHREADS, SMEM_BYTES>>>(p, tmX, tmW, tmWo, tmQ, tmXh, tmWh);
  } else {
    fused_kernel<0><<<4, NTHREADS, SMEM_BYTES>>>(p, tmX, tmW, tmWo, tmQ, tmXh, tmWh);
    fused_kernel<1><<<NCTA, NTHREADS, SMEM_BYTES>>>(p, tmX, tmW, tmWo, tmQ, tmXh, tmWh);
    fused_kernel<2><<<NCTA, NTHREADS, SMEM_BYTES>>>(p, tmX, tmW, tmWo, tmQ, tmXh, tmWh);
  }
}
```

```cpp
#include <cuda_runtime.h>
#include <cuda.h>
#include <cuda_bf16.h>
#include <stdint.h>

namespace {

constexpr int SEQ = 2048;
constexpr int DM = 1024;
constexpr int NCTA = 132;
constexpr int NTHREADS = 384;

constexpr int STG1A = 32768;
constexpr int NS1A = 3;
constexpr int STG1B = 12288;
constexpr int NS1B = 5;
constexpr int OFF_1B = NS1A * STG1A;
constexpr int STG2 = 32768;
constexpr int NS2 = 5;
constexpr int STGH = 73728;
constexpr int OFF_VP = 0;
constexpr int OFF_KH = 1 * STG2;
constexpr int OFF_OP = 2 * STG2;
constexpr int OFF_Q = 3 * STG2;
constexpr int T_A4 = 0, T_TW = 16384, T_B2 = 24576, T_A1 = 28672, T_END = 32768;
constexpr int OFF_U = 163840;
constexpr int OFF_H = OFF_U + 32768;
constexpr int OFF_T = OFF_U - T_END;
constexpr int OFF_LAND = 4 * STG2;
constexpr int OFF_BAR = OFF_H + 32768;
constexpr int OFF_SC = OFF_BAR + 512;
constexpr int OFF_L0 = OFF_BAR + 1024;
constexpr int SMEM_BYTES = OFF_L0 + 2048;
static_assert(OFF_T + T_A1 == OFF_1B + NS1B * STG1B && OFF_T + T_TW == OFF_1B + 4 * STG1B && OFF_LAND == OFF_T + T_A4, "layout");
static_assert(3 * STGH <= OFF_BAR && SMEM_BYTES <= 232448, "smem");

constexpr int BAR_FULLA = 0;
constexpr int BAR_EMPTYA = 3;
constexpr int BAR_FULLB = 6;
constexpr int BAR_EMPTYB = 11;
constexpr int BAR_FULL2 = 16;
constexpr int BAR_EMPTY2 = 21;
constexpr int BAR_T = 26;
constexpr int BAR_UH = 27;
constexpr int BAR_LFREE = 28;
constexpr int BAR_LAND = 29;
constexpr int BAR_U = 30;
constexpr int BAR_Q = 31;
constexpr int BAR_STG = 32;
constexpr int BAR_DEAD = 33;
constexpr int BAR_X = 35;
constexpr int BAR_REL = 36;

constexpr int NB_G1DONE = 1;
constexpr int NB_OREADY = 2;
constexpr int NB_WG = 4;
constexpr int NB_HELP3 = 6;
constexpr int NB_FIRST = 7;

#define PACE 480u
#define PF0 20
#define SCHED 1
#define REG_MATH 224
#define REG_HELP 56
constexpr int SPIN_LIMIT = 1 << 20;

__device__ __align__(1024) __nv_bfloat16 g_o[SEQ * DM];
__device__ uint32_t g_flag_o[256];
__device__ uint32_t g_flag_h[4];
__device__ uint4 g_halo[128 * 128];
__device__ __align__(128) const uint32_t g_tab[T_END / 4] = {
0x3c003c00,0x3bf13bff,0,0xafd6a648,0x3c003c00,0x3b993bce,0,0xb505b303,0x3c003c00,0x3af63b50,0,0xb7e3b67c,
0x3c003c00,0x3a0f3a8a,0,0xb93ab89b,0x3bc33bfe,0x3b773bfa,0xb3c6aa48,0xb5c2acb5,0x3a6d3b3b,0x389b3a4f,0xb8c4b6d7,0xba8ab8ec,
0x381d395f,0x26483505,0xbaddb9ed,0xbbffbb99,0x30b23564,0xb848b444,0xbbeabb88,0xbac2bbb6,0x3b0e3bf6,0x3a8a3bf1,0xb78bae46,0xb89bafd6,
0x34a53913,0xa6483732,0xbba8ba2f,0xbbffbb25,0xb78bae46,0xbac2b7e3,0xbb0ebbf6,0xb848baf6,0xbba8ba2f,0xbb50bbfa,0xb4a5b913,0x367cacb5,
0x39ed3bea,0x393a3be2,0xb95fb0b2,0xba0fb179,0xb56433c6,0xb8ec2648,0xbb88bbc3,0xba4fbbff,0xbbfeba6d,0xbb25bbce,0xaa48b8c4,0x3732b303,
0xb6d7badd,0x3444b67c,0x3b3b381d,0x3bb63b50,0x38723bd9,0x37323bce,0xbaa7b23e,0xbb25b303,0xbaa7b23e,0xbbb6b67c,0xb872bbd9,0xb444bb50,
0xb872bbd9,0xacb5ba8a,0x3aa7323e,0x3bfa389b,0x3aa7323e,0x3bf139cb,0x38723bd9,0xafd63984,0x35643bc3,0x33033bb6,0xbb88b3c6,0xbbceb444,
0xbbfeb8c4,0xbb77ba0f,0x2a48ba6d,0x35c2b93a,0x36d7b81d,0x3a8aafd6,0x3b3b3add,0x389b3bf1,0x395f3bea,0x26483b25,0xb9ed30b2,0xbbffb732,
0x2e463ba8,0xa6483b99,0xbbf6b4a5,0xbbffb505,0xba2fbb0e,0xb848bbb6,0x3913b78b,0x3ac2b444,0x3bf634a5,0x3b50393a,0x2e463ba8,0xb67c3a0f,
0xb913378b,0xbbe2afd6,0xba2fbb0e,0xb179bbf1,0xb0b23b88,0xb4443b77,0xbbeab564,0xbbb6b5c2,0xb3c6bbfe,0x2cb5bbe2,0x3bc3aa48,0x3bfa3179,
0x38c43b3b,0x2fd63bff,0xba6d36d7,0xbbf12648,0xbaddb95f,0xb505bbce,0x381db9ed,0x3b99b303,0xb61f3b64,0xb7e33b50,0xbb64b61f,0xbaf6b67c,
0x361fbb64,0x393aba8a,0x3b64361f,0x3a0f389b,0xb61f3b64,0xba4f3984,0xbb64b61f,0xb8ecb9cb,0x361fbb64,0x3b25b848,0x3b64361f,0x37323ac2,
0xb8c43b3b,0xb9843b25,0xba6db6d7,0xb9cbb732,0x3addb95f,0x3bceb7e3,0x381d39ed,0x33033af6,0xbbea3564,0xbb77acb5,0xb0b2bb88,0x35c2bbfa,
0x3bc32a48,0x389b38ec,0xb3c63bfe,0xba8a3a4f,0xba2f3b0e,0xbac23af6,0xb913b78b,0xb848b7e3,0x3bf6b4a5,0x3b50acb5,0xae463ba8,0xb67c3bfa,
0xb913b78b,0xb179ba4f,0x3a2fbb0e,0x3be2b8ec,0xae463ba8,0xb9cb3b99,0xbbf634a5,0xb984b505,0xbb3b3add,0xbb993ac2,0xb6d7b81d,0xb505b848,
0x39ed30b2,0x37e335c2,0xb95f3bea,0xbaf63b77,0x3564bbc3,0x3a0fbbe2,0x3b88b3c6,0x393a3179,0xbbfe38c4,0xba4f2648,0xaa48ba6d,0x38ecbbff,
0xbbd93aa7,0xbbfa3a8a,0xb23eb872,0xacb5b89b,0x323e3872,0xafd639cb,0xbbd93aa7,0xbbf13984,0x3bd9baa7,0x3b99b848,0x323e3872,0xb5053ac2,
0xb23eb872,0x37e3bb77,0x3bd9baa7,0x3af6b5c2,0xbbfe3a6d,0xbbe23a4f,0x2a48b8c4,0x3179b8ec,0xb6d73add,0xb9843b99,0xbb3b381d,0xb9cb3505,
0x395fb0b2,0x33033444,0xb9ed3bea,0xbbce3bb6,0x3b88bbc3,0x3b77b93a,0x356433c6,0xb5c23a0f,0xbba83a2f,0xbb503a0f,0x34a5b913,0x367cb93a,
0xbb0e3bf6,0xbbe23bf1,0xb78b2e46,0xb179afd6,0xb4a53913,0xb9cb3b25,0xbba83a2f,0xb9843732,0x378bae46,0xb30337e3,0xbb0e3bf6,0xbbce3af6,
0xbadd39ed,0xba4f39cb,0x381db95f,0x38ecb984,0xbbea3b88,0xbb253ac2,0x30b2b564,0x3732b848,0xbbc33bfe,0xbbb63b77,0xb3c62a48,0x3444b5c2,
0xba6d3b3b,0xbbfa3be2,0xb8c436d7,0x2cb5b179,0xb9a839a8,0xb8ec3984,0x39a8b9a8,0x3a4fb9cb,0xb9a839a8,0xb7323848,0x39a8b9a8,0x3b25bac2,
0xb9a839a8,0xb44435c2,0x39a8b9a8,0x3bb6bb77,0xb9a839a8,0xacb53179,0x39a8b9a8,0x3bfabbe2,0xb81d395f,0xb67c393a,0x3addb9ed,0x3b50ba0f,
0xb0b23564,0x31792fd6,0x3beabb88,0x3be2bbf1,0x33c6aa48,0x3984b732,0x3bc3bbfe,0x39cbbb25,0x38c4b6d7,0x3bcebaf6,0x3a6dbb3b,0x3303b7e3,
0xb4a53913,0xb17938ec,0x3ba8ba2f,0x3be2ba4f,0x378bae46,0x39cbb505,0x3b0ebbf6,0x3984bb99,0x3ba8ba2f,0x3bcebbb6,0x34a5b913,0xb303b444,
0x3b0ebbf6,0x35c2ba0f,0xb78b2e46,0xbb77393a,0xaa4838c4,0x2cb5389b,0x3bfeba6d,0x3bfaba8a,0x3b3bb81d,0x3bf1b984,0x36d7badd,0x2fd6b9cb,
0x39edbbea,0x3505bac2,0xb95f30b2,0xbb993848,0xb564b3c6,0xbaf635c2,0xbb883bc3,0xb7e33b77,0x323e3872,0x35053848,0x3bd9baa7,0x3b99bac2,
0x3bd9baa7,0x3af6bb77,0xb23eb872,0xb7e3b5c2,0xb23eb872,0xb93ab179,0xbbd93aa7,0xba0f3be2,0xbbd93aa7,0xb8ec3bff,0x323e3872,0x3a4fa648,
0x36d7381d,0x384837e3,0x3b3bbadd,0x3ac2baf6,0x395fbbea,0x367cbbfa,0xb9edb0b2,0xbb502cb5,0xbb8833c6,0xbbe238ec,0xb5643bc3,0x31793a4f,
0x2a483a6d,0x39843505,0x3bfeb8c4,0x39cbbb99,0x3913378b,0x39cb3732,0x3a2fbb0e,0x3984bb25,0x2e46bba8,0xb303baf6,0xbbf634a5,0xbbce37e3,
0xba2f3b0e,0xb5c23bfa,0x3913378b,0x3b772cb5,0x3bf6b4a5,0x3a8aba4f,0x2e46bba8,0xb89bb8ec,0x3a6d36d7,0x3af6367c,0x38c4bb3b,0x37e3bb50,
0xb81db9ed,0xba0fb89b,0xbadd395f,0xb93a3a8a,0x30b23b88,0x38ec39cb,0x3beab564,0x3a4fb984,0x33c6bbfe,0xb732bac2,0xbbc3aa48,0xbb253848,
0x3b64361f,0x3bb635c2,0x361fbb64,0x3444bb77,0xbb64b61f,0xbbfab179,0xb61f3b64,0xacb53be2,0x3b64361f,0x3bf1a648,0x361fbb64,0xafd6bbff,
0xbb64b61f,0xbb993303,0xb61f3b64,0x35053bce,0x3bea3564,0x3bff3505,0x30b2bb88,0x2648bb99,0xbbc32a48,0xbac23444,0x33c63bfe,0x38483bb6,
0x3a6db6d7,0x367cba0f,0xb8c4bb3b,0xbb50b93a,0xb81d39ed,0x31793bf1,0x3add395f,0x3be22fd6,0x3bf634a5,0x3bce3444,0xae46bba8,0xb303bbb6,
0xb913378b,0xb5c2393a,0x3a2f3b0e,0x3b773a0f,0xae46bba8,0xb89bbbf1,0xbbf6b4a5,0xba8a2fd6,0x3a2f3b0e,0x3bff3732,0x3913b78b,0xa648bb25,
0x3b8833c6,0x3b253303,0xb564bbc3,0xb732bbce,0xaa483a6d,0x34443b50,0x3bfe38c4,0x3bb6367c,0xbb3bbadd,0xbbfab89b,0xb6d7381d,0x2cb53a8a,
0x39edb0b2,0x2fd6b984,0xb95fbbea,0xbbf1b9cb,0x3aa7323e,0x3a0f3179,0xb872bbd9,0xb93abbe2,0x38723bd9,0x3a4f3bff,0x3aa7323e,0x38eca648,
0xbaa7b23e,0xb7323303,0x38723bd9,0x3b253bce,0xb872bbd9,0xbbb6bb50,0xbaa7b23e,0xb444367c,0x395f30b2,0x389b2fd6,0xb9edbbea,0xba8abbf1,
0x3b883bc3,0x3bff3b25,0x3564b3c6,0x2648b732,0x2a4838c4,0x38483af6,0x3bfe3a6d,0x3ac237e3,0xbb3bb81d,0xb67c2cb5,0x36d73add,0x3b503bfa,
0x378b2e46,0x35c22cb5,0xbb0ebbf6,0xbb77bbfa,0x3ba83a2f,0x3a8a38ec,0xb4a5b913,0xb89bba4f,0x3b0e3bf6,0x3bff3b99,0x378b2e46,0xa648b505,
0x34a53913,0x3ac23bb6,0x3ba83a2f,0x38483444,0x33c62a48,0x2fd62648,0xbbc3bbfe,0xbbf1bbff,0x38c436d7,0x35053303,0xba6dbb3b,0xbb99bbce,
0x3add39ed,0x37e3367c,0xb81db95f,0xbaf6bb50,0x3bea3b88,0x393a389b,0xb0b2b564,0xba0fba8a,0x3c003c00,0xbbf1bbff,0,0x2fd62648,
0x3c003c00,0xbb99bbce,0,0x35053303,0x3c003c00,0xbaf6bb50,0,0x37e3367c,0x3c003c00,0xba0fba8a,0,0x393a389b,
0x3bc33bfe,0xbb77bbfa,0xb3c6aa48,0x35c22cb5,0x3a6d3b3b,0xb89bba4f,0xb8c4b6d7,0x3a8a38ec,0x381d395f,0xa648b505,0xbaddb9ed,0x3bff3b99,
0x30b23564,0x38483444,0xbbeabb88,0x3ac23bb6,0x3b0e3bf6,0xba8abbf1,0xb78bae46,0x389b2fd6,0x34a53913,0x2648b732,0xbba8ba2f,0x3bff3b25,
0xb78bae46,0x3ac237e3,0xbb0ebbf6,0x38483af6,0xbba8ba2f,0x3b503bfa,0xb4a5b913,0xb67c2cb5,0x39ed3bea,0xb93abbe2,0xb95fb0b2,0x3a0f3179,
0xb56433c6,0x38eca648,0xbb88bbc3,0x3a4f3bff,0xbbfeba6d,0x3b253bce,0xaa48b8c4,0xb7323303,0xb6d7badd,0xb444367c,0x3b3b381d,0xbbb6bb50,
0x38723bd9,0xb732bbce,0xbaa7b23e,0x3b253303,0xbaa7b23e,0x3bb6367c,0xb872bbd9,0x34443b50,0xb872bbd9,0x2cb53a8a,0x3aa7323e,0xbbfab89b,
0x3aa7323e,0xbbf1b9cb,0x38723bd9,0x2fd6b984,0x35643bc3,0xb303bbb6,0xbb88b3c6,0x3bce3444,0xbbfeb8c4,0x3b773a0f,0x2a48ba6d,0xb5c2393a,
0x36d7b81d,0xba8a2fd6,0x3b3b3add,0xb89bbbf1,0x395f3bea,0xa648bb25,0xb9ed30b2,0x3bff3732,0x2e463ba8,0x2648bb99,0xbbf6b4a5,0x3bff3505,
0xba2fbb0e,0x38483bb6,0x3913b78b,0xbac23444,0x3bf634a5,0xbb50b93a,0x2e463ba8,0x367cba0f,0xb913378b,0x3be22fd6,0xba2fbb0e,0x31793bf1,
0xb0b23b88,0x3444bb77,0xbbeab564,0x3bb635c2,0xb3c6bbfe,0xacb53be2,0x3bc3aa48,0xbbfab179,0x38c43b3b,0xafd6bbff,0xba6d36d7,0x3bf1a648,
0xbaddb95f,0x35053bce,0x381db9ed,0xbb993303,0xb61f3b64,0x37e3bb50,0xbb64b61f,0x3af6367c,0x361fbb64,0xb93a3a8a,0x3b64361f,0xba0fb89b,
0xb61f3b64,0x3a4fb984,0xbb64b61f,0x38ec39cb,0x361fbb64,0xbb253848,0x3b64361f,0xb732bac2,0xb8c43b3b,0x3984bb25,0xba6db6d7,0x39cb3732,
0x3addb95f,0xbbce37e3,0x381d39ed,0xb303baf6,0xbbea3564,0x3b772cb5,0xb0b2bb88,0xb5c23bfa,0x3bc32a48,0xb89bb8ec,0xb3c63bfe,0x3a8aba4f,
0xba2f3b0e,0x3ac2baf6,0xb913b78b,0x384837e3,0x3bf6b4a5,0xbb502cb5,0xae463ba8,0x367cbbfa,0xb913b78b,0x31793a4f,0x3a2fbb0e,0xbbe238ec,
0xae463ba8,0x39cbbb99,0xbbf634a5,0x39843505,0xbb3b3add,0x3b99bac2,0xb6d7b81d,0x35053848,0x39ed30b2,0xb7e3b5c2,0xb95f3bea,0x3af6bb77,
0x3564bbc3,0xba0f3be2,0x3b88b3c6,0xb93ab179,0xbbfe38c4,0x3a4fa648,0xaa48ba6d,0xb8ec3bff,0xbbd93aa7,0x3bfaba8a,0xb23eb872,0x2cb5389b,
0x323e3872,0x2fd6b9cb,0xbbd93aa7,0x3bf1b984,0x3bd9baa7,0xbb993848,0x323e3872,0x3505bac2,0xb23eb872,0xb7e33b77,0x3bd9baa7,0xbaf635c2,
0xbbfe3a6d,0x3be2ba4f,0x2a48b8c4,0xb17938ec,0xb6d73add,0x3984bb99,0xbb3b381d,0x39cbb505,0x395fb0b2,0xb303b444,0xb9ed3bea,0x3bcebbb6,
0x3b88bbc3,0xbb77393a,0x356433c6,0x35c2ba0f,0xbba83a2f,0x3b50ba0f,0x34a5b913,0xb67c393a,0xbb0e3bf6,0x3be2bbf1,0xb78b2e46,0x31792fd6,
0xb4a53913,0x39cbbb25,0xbba83a2f,0x3984b732,0x378bae46,0x3303b7e3,0xbb0e3bf6,0x3bcebaf6,0xbadd39ed,0x3a4fb9cb,0x381db95f,0xb8ec3984,
0xbbea3b88,0x3b25bac2,0x30b2b564,0xb7323848,0xbbc33bfe,0x3bb6bb77,0xb3c62a48,0xb44435c2,0xba6d3b3b,0x3bfabbe2,0xb8c436d7,0xacb53179,
0xb9a839a8,0x38ecb984,0x39a8b9a8,0xba4f39cb,0xb9a839a8,0x3732b848,0x39a8b9a8,0xbb253ac2,0xb9a839a8,0x3444b5c2,0x39a8b9a8,0xbbb63b77,
0xb9a839a8,0x2cb5b179,0x39a8b9a8,0xbbfa3be2,0xb81d395f,0x367cb93a,0x3addb9ed,0xbb503a0f,0xb0b23564,0xb179afd6,0x3beabb88,0xbbe23bf1,
0x33c6aa48,0xb9843732,0x3bc3bbfe,0xb9cb3b25,0x38c4b6d7,0xbbce3af6,0x3a6dbb3b,0xb30337e3,0xb4a53913,0x3179b8ec,0x3ba8ba2f,0xbbe23a4f,
0x378bae46,0xb9cb3505,0x3b0ebbf6,0xb9843b99,0x3ba8ba2f,0xbbce3bb6,0x34a5b913,0x33033444,0x3b0ebbf6,0xb5c23a0f,0xb78b2e46,0x3b77b93a,
0xaa4838c4,0xacb5b89b,0x3bfeba6d,0xbbfa3a8a,0x3b3bb81d,0xbbf13984,0x36d7badd,0xafd639cb,0x39edbbea,0xb5053ac2,0xb95f30b2,0x3b99b848,
0xb564b3c6,0x3af6b5c2,0xbb883bc3,0x37e3bb77,0x323e3872,0xb505b848,0x3bd9baa7,0xbb993ac2,0x3bd9baa7,0xbaf63b77,0xb23eb872,0x37e335c2,
0xb23eb872,0x393a3179,0xbbd93aa7,0x3a0fbbe2,0xbbd93aa7,0x38ecbbff,0x323e3872,0xba4f2648,0x36d7381d,0xb848b7e3,0x3b3bbadd,0xbac23af6,
0x395fbbea,0xb67c3bfa,0xb9edb0b2,0x3b50acb5,0xbb8833c6,0x3be2b8ec,0xb5643bc3,0xb179ba4f,0x2a483a6d,0xb984b505,0x3bfeb8c4,0xb9cb3b99,
0x3913378b,0xb9cbb732,0x3a2fbb0e,0xb9843b25,0x2e46bba8,0x33033af6,0xbbf634a5,0x3bceb7e3,0xba2f3b0e,0x35c2bbfa,0x3913378b,0xbb77acb5,
0x3bf6b4a5,0xba8a3a4f,0x2e46bba8,0x389b38ec,0x3a6d36d7,0xbaf6b67c,0x38c4bb3b,0xb7e33b50,0xb81db9ed,0x3a0f389b,0xbadd395f,0x393aba8a,
0x30b23b88,0xb8ecb9cb,0x3beab564,0xba4f3984,0x33c6bbfe,0x37323ac2,0xbbc3aa48,0x3b25b848,0x3b64361f,0xbbb6b5c2,0x361fbb64,0xb4443b77,
0xbb64b61f,0x3bfa3179,0xb61f3b64,0x2cb5bbe2,0x3b64361f,0xbbf12648,0x361fbb64,0x2fd63bff,0xbb64b61f,0x3b99b303,0xb61f3b64,0xb505bbce,
0x3bea3564,0xbbffb505,0x30b2bb88,0xa6483b99,0xbbc32a48,0x3ac2b444,0x33c63bfe,0xb848bbb6,0x3a6db6d7,0xb67c3a0f,0xb8c4bb3b,0x3b50393a,
0xb81d39ed,0xb179bbf1,0x3add395f,0xbbe2afd6,0x3bf634a5,0xbbceb444,0xae46bba8,0x33033bb6,0xb913378b,0x35c2b93a,0x3a2f3b0e,0xbb77ba0f,
0xae46bba8,0x389b3bf1,0xbbf6b4a5,0x3a8aafd6,0x3a2f3b0e,0xbbffb732,0x3913b78b,0x26483b25,0x3b8833c6,0xbb25b303,0xb564bbc3,0x37323bce,
0xaa483a6d,0xb444bb50,0x3bfe38c4,0xbbb6b67c,0xbb3bbadd,0x3bfa389b,0xb6d7381d,0xacb5ba8a,0x39edb0b2,0xafd63984,0xb95fbbea,0x3bf139cb,
0x3aa7323e,0xba0fb179,0xb872bbd9,0x393a3be2,0x38723bd9,0xba4fbbff,0x3aa7323e,0xb8ec2648,0xbaa7b23e,0x3732b303,0x38723bd9,0xbb25bbce,
0xb872bbd9,0x3bb63b50,0xbaa7b23e,0x3444b67c,0x395f30b2,0xb89bafd6,0xb9edbbea,0x3a8a3bf1,0x3b883bc3,0xbbffbb25,0x3564b3c6,0xa6483732,
0x2a4838c4,0xb848baf6,0x3bfe3a6d,0xbac2b7e3,0xbb3bb81d,0x367cacb5,0x36d73add,0xbb50bbfa,0x378b2e46,0xb5c2acb5,0xbb0ebbf6,0x3b773bfa,
0x3ba83a2f,0xba8ab8ec,0xb4a5b913,0x389b3a4f,0x3b0e3bf6,0xbbffbb99,0x378b2e46,0x26483505,0x34a53913,0xbac2bbb6,0x3ba83a2f,0xb848b444,
0x33c62a48,0xafd6a648,0xbbc3bbfe,0x3bf13bff,0x38c436d7,0xb505b303,0xba6dbb3b,0x3b993bce,0x3add39ed,0xb7e3b67c,0xb81db95f,0x3af63b50,
0x3bea3b88,0xb93ab89b,0xb0b2b564,0x3a0f3a8a,0x3c003c00,0x38ec3984,0,0xba4fb9cb,0x3c003c00,0x37323848,0,0xbb25bac2,
0x3c003c00,0x344435c2,0,0xbbb6bb77,0x3c003c00,0x2cb53179,0,0xbbfabbe2,0xb3c6aa48,0xbb50ba0f,0xbbc3bbfe,0xb67cb93a,
0xb8c4b6d7,0xbbe2bbf1,0xba6dbb3b,0x3179afd6,0xbaddb9ed,0xb9cbbb25,0xb81db95f,0x39843732,0xbbeabb88,0xb303b7e3,0xb0b2b564,0x3bce3af6,
0xbb0ebbf6,0xb179b8ec,0x378b2e46,0x3be23a4f,0xb4a5b913,0x39cb3505,0x3ba83a2f,0x39843b99,0x378b2e46,0x3bce3bb6,0x3b0e3bf6,0xb3033444,
0x3ba83a2f,0x35c23a0f,0x34a53913,0xbb77b93a,0x395f30b2,0x3bfa3a8a,0x39ed3bea,0xacb5389b,0x3b883bc3,0x2fd639cb,0xb56433c6,0xbbf1b984,
0x2a4838c4,0xbb99b848,0xbbfeba6d,0xb505bac2,0xbb3bb81d,0xb7e3bb77,0xb6d7badd,0x3af635c2,0x38723bd9,0xb5053848,0xbaa7b23e,0xbb99bac2,
0xbaa7b23e,0xbaf6bb77,0xb872bbd9,0x37e3b5c2,0xb872bbd9,0x393ab179,0x3aa7323e,0x3a0f3be2,0x3aa7323e,0x38ec3bff,0x38723bd9,0xba4fa648,
0xbb88b3c6,0xbac2baf6,0xb564bbc3,0x3848b7e3,0x2a48ba6d,0x3b502cb5,0x3bfe38c4,0x367c3bfa,0x3b3b3add,0xb1793a4f,0xb6d7381d,0xbbe2b8ec,
0xb9ed30b2,0xb9cbbb99,0xb95fbbea,0x3984b505,0xae46bba8,0x39cbb732,0x3bf634a5,0x39843b25,0x3a2f3b0e,0xb3033af6,0xb913378b,0xbbceb7e3,
0xbbf6b4a5,0xb5c2bbfa,0xae46bba8,0x3b77acb5,0x3913b78b,0x3a8a3a4f,0x3a2f3b0e,0xb89b38ec,0x3bea3564,0x37e33b50,0xb0b23b88,0xbaf6367c,
0xbbc32a48,0xb93aba8a,0xb3c6bbfe,0x3a0fb89b,0x3a6db6d7,0x3a4f3984,0x38c43b3b,0xb8ec39cb,0xb81d39ed,0xbb25b848,0xbaddb95f,0x3732bac2,
0xb61f3b64,0xbbb635c2,0xbb64b61f,0xb444bb77,0x361fbb64,0x3bfab179,0x3b64361f,0x2cb53be2,0xb61f3b64,0xbbf1a648,0xbb64b61f,0x2fd6bbff,
0x361fbb64,0x3b993303,0x3b64361f,0xb5053bce,0xba6db6d7,0xa648bb99,0x38c4bb3b,0x3bffb505,0x381d39ed,0xb8483bb6,0xbadd395f,0xbac2b444,
0xb0b2bb88,0x3b50b93a,0x3beab564,0x367c3a0f,0xb3c63bfe,0xbbe22fd6,0xbbc3aa48,0x3179bbf1,0x3a2fbb0e,0x3bceb444,0x3913378b,0xb3033bb6,
0xbbf634a5,0xb5c2b93a,0x2e46bba8,0x3b77ba0f,0x3913378b,0xb89b3bf1,0xba2f3b0e,0xba8aafd6,0x2e46bba8,0x3bffb732,0x3bf6b4a5,0xa6483b25,
0x36d7381d,0xb7323bce,0xbb3b3add,0xbb253303,0x395fbbea,0x3bb6b67c,0x39ed30b2,0xb4443b50,0xbb8833c6,0x2cb5ba8a,0x3564bbc3,0x3bfab89b,
0x2a483a6d,0xbbf139cb,0xbbfe38c4,0xafd6b984,0xbbd93aa7,0xba0f3179,0xb23eb872,0x393abbe2,0x323e3872,0xba4f3bff,0xbbd93aa7,0xb8eca648,
0x3bd9baa7,0x37323303,0x323e3872,0xbb253bce,0xb23eb872,0x3bb6bb50,0x3bd9baa7,0x3444367c,0x2a48b8c4,0x3a8abbf1,0x3bfeba6d,0x389bafd6,
0xbb3b381d,0xa648b732,0x36d7badd,0x3bffbb25,0xb9ed3bea,0xbac237e3,0xb95f30b2,0x3848baf6,0x356433c6,0xbb503bfa,0xbb883bc3,0xb67cacb5,
0x3ba8ba2f,0x35c2acb5,0xb4a53913,0xbb773bfa,0x3b0ebbf6,0x3a8ab8ec,0x378bae46,0xb89b3a4f,0x34a5b913,0x3bffbb99,0x3ba8ba2f,0xa6483505,
0xb78b2e46,0x3ac2bbb6,0x3b0ebbf6,0x3848b444,0xb81d395f,0xbbf13bff,0xbadd39ed,0xafd62648,0xb0b23564,0xbb993bce,0xbbea3b88,0xb5053303,
0x33c6aa48,0xbaf63b50,0xbbc33bfe,0xb7e3367c,0x38c4b6d7,0xba0f3a8a,0xba6d3b3b,0xb93a389b,0xb9a839a8,0x2fd6a648,0x39a8b9a8,0x3bf1bbff,
0xb9a839a8,0x3505b303,0x39a8b9a8,0x3b99bbce,0xb9a839a8,0x37e3b67c,0x39a8b9a8,0x3af6bb50,0xb9a839a8,0x393ab89b,0x39a8b9a8,0x3a0fba8a,
0x3addb9ed,0x3b77bbfa,0x381db95f,0xb5c22cb5,0x3beabb88,0x389bba4f,0x30b2b564,0xba8a38ec,0x3bc3bbfe,0x2648b505,0xb3c62a48,0xbbff3b99,
0x3a6dbb3b,0xb8483444,0xb8c436d7,0xbac23bb6,0x34a5b913,0xb89b2fd6,0xbba83a2f,0xba8a3bf1,0xb78b2e46,0xbbff3b25,0xbb0e3bf6,0x26483732,
0xbba83a2f,0xb8483af6,0xb4a53913,0x3ac2b7e3,0xbb0e3bf6,0x367c2cb5,0x378bae46,0x3b50bbfa,0xbbfe3a6d,0xb93a3be2,0xaa4838c4,0x3a0fb179,
0xb6d73add,0x38ec2648,0x3b3bb81d,0x3a4fbbff,0x395fb0b2,0x3b25bbce,0x39edbbea,0xb732b303,0x3b88bbc3,0xb444b67c,0xb564b3c6,0xbbb63b50,
0x323e3872,0x3b25b303,0x3bd9baa7,0x3732bbce,0x3bd9baa7,0x3444bb50,0xb23eb872,0xbbb6367c,0xb23eb872,0xbbfa389b,0xbbd93aa7,0xacb53a8a,
0xbbd93aa7,0x2fd63984,0x323e3872,0x3bf1b9cb,0x3b3bbadd,0x3303bbb6,0xb6d7b81d,0xbbce3444,0xb9edb0b2,0xbb773a0f,0xb95f3bea,0x35c2393a,
0xb5643bc3,0x3a8a2fd6,0x3b88b3c6,0x389bbbf1,0x3bfeb8c4,0x2648bb25,0xaa48ba6d,0xbbff3732,0xb913b78b,0xbbff3505,0xba2f3b0e,0x26483b99,
0xae463ba8,0x3ac23444,0x3bf6b4a5,0x3848bbb6,0x3a2fbb0e,0xb67cba0f,0xb913b78b,0xbb50393a,0xbbf634a5,0xb1793bf1,0xae463ba8,0x3be2afd6,
0xb8c43b3b,0x34443b77,0x3a6d36d7,0x3bb6b5c2,0x3addb95f,0xacb5bbe2,0xb81db9ed,0xbbfa3179,0xbbea3564,0xafd63bff,0x30b23b88,0x3bf12648,
0x3bc32a48,0x3505bbce,0x33c6bbfe,0xbb99b303,0x3b64361f,0x3af6b67c,0x361fbb64,0xb7e3bb50,0xbb64b61f,0xba0f389b,0xb61f3b64,0x393a3a8a,
0x3b64361f,0x38ecb9cb,0x361fbb64,0xba4fb984,0xbb64b61f,0xb7323ac2,0xb61f3b64,0x3b253848,0x30b2bb88,0xb984bb25,0xbbeab564,0xb9cb3732,
0x33c63bfe,0x3bce37e3,0x3bc3aa48,0x3303baf6,0xb8c4bb3b,0xbb772cb5,0xba6d36d7,0x35c23bfa,0x3add395f,0x389bb8ec,0x381db9ed,0xba8aba4f,
0xbbf6b4a5,0xb84837e3,0x2e463ba8,0x3ac23af6,0x3913b78b,0xb67cbbfa,0xba2fbb0e,0xbb50acb5,0x2e463ba8,0x3be238ec,0x3bf634a5,0x3179ba4f,
0xba2fbb0e,0xb9843505,0xb913378b,0x39cb3b99,0x35643bc3,0x3b993ac2,0x3b8833c6,0x3505b848,0xbbfeb8c4,0xb7e335c2,0xaa483a6d,0x3af63b77,
0x36d7b81d,0xba0fbbe2,0xbb3bbadd,0xb93a3179,0x395f3bea,0x3a4f2648,0x39edb0b2,0xb8ecbbff,0x3aa7323e,0x2cb5b89b,0xb872bbd9,0xbbfaba8a,
0x38723bd9,0x3bf13984,0x3aa7323e,0xafd6b9cb,0xbaa7b23e,0x35053ac2,0x38723bd9,0x3b993848,0xb872bbd9,0xbaf6b5c2,0xbaa7b23e,0x37e33b77,
0xb9edbbea,0xbbe2ba4f,0xb95fb0b2,0x317938ec,0x3564b3c6,0xb984bb99,0xbb88bbc3,0xb9cbb505,0x3bfe3a6d,0x3303b444,0xaa48b8c4,0xbbcebbb6,
0x36d73add,0x3b77393a,0x3b3b381d,0xb5c2ba0f,0xb78bae46,0x367c393a,0x3b0e3bf6,0x3b503a0f,0xbba8ba2f,0xb1792fd6,0x34a53913,0x3be23bf1,
0xbb0ebbf6,0xb984b732,0xb78bae46,0x39cb3b25,0xb4a5b913,0xbbcebaf6,0xbba8ba2f,0x330337e3,0x3bc33bfe,0x3a4f39cb,0x33c62a48,0xb8ecb984,
0x3a6d3b3b,0x3b253ac2,0x38c436d7,0xb732b848,0x381d395f,0x3bb63b77,0x3add39ed,0xb444b5c2,0x30b23564,0x3bfa3be2,0x3bea3b88,0xacb5b179,
0x3c003c00,0xb8ecb984,0,0x3a4f39cb,0x3c003c00,0xb732b848,0,0x3b253ac2,0x3c003c00,0xb444b5c2,0,0x3bb63b77,
0x3c003c00,0xacb5b179,0,0x3bfa3be2,0xb3c6aa48,0x3b503a0f,0xbbc3bbfe,0x367c393a,0xb8c4b6d7,0x3be23bf1,0xba6dbb3b,0xb1792fd6,
0xbaddb9ed,0x39cb3b25,0xb81db95f,0xb984b732,0xbbeabb88,0x330337e3,0xb0b2b564,0xbbcebaf6,0xbb0ebbf6,0x317938ec,0x378b2e46,0xbbe2ba4f,
0xb4a5b913,0xb9cbb505,0x3ba83a2f,0xb984bb99,0x378b2e46,0xbbcebbb6,0x3b0e3bf6,0x3303b444,0x3ba83a2f,0xb5c2ba0f,0x34a53913,0x3b77393a,
0x395f30b2,0xbbfaba8a,0x39ed3bea,0x2cb5b89b,0x3b883bc3,0xafd6b9cb,0xb56433c6,0x3bf13984,0x2a4838c4,0x3b993848,0xbbfeba6d,0x35053ac2,
0xbb3bb81d,0x37e33b77,0xb6d7badd,0xbaf6b5c2,0x38723bd9,0x3505b848,0xbaa7b23e,0x3b993ac2,0xbaa7b23e,0x3af63b77,0xb872bbd9,0xb7e335c2,
0xb872bbd9,0xb93a3179,0x3aa7323e,0xba0fbbe2,0x3aa7323e,0xb8ecbbff,0x38723bd9,0x3a4f2648,0xbb88b3c6,0x3ac23af6,0xb564bbc3,0xb84837e3,
0x2a48ba6d,0xbb50acb5,0x3bfe38c4,0xb67cbbfa,0x3b3b3add,0x3179ba4f,0xb6d7381d,0x3be238ec,0xb9ed30b2,0x39cb3b99,0xb95fbbea,0xb9843505,
0xae46bba8,0xb9cb3732,0x3bf634a5,0xb984bb25,0x3a2f3b0e,0x3303baf6,0xb913378b,0x3bce37e3,0xbbf6b4a5,0x35c23bfa,0xae46bba8,0xbb772cb5,
0x3913b78b,0xba8aba4f,0x3a2f3b0e,0x389bb8ec,0x3bea3564,0xb7e3bb50,0xb0b23b88,0x3af6b67c,0xbbc32a48,0x393a3a8a,0xb3c6bbfe,0xba0f389b,
0x3a6db6d7,0xba4fb984,0x38c43b3b,0x38ecb9cb,0xb81d39ed,0x3b253848,0xbaddb95f,0xb7323ac2,0xb61f3b64,0x3bb6b5c2,0xbb64b61f,0x34443b77,
0x361fbb64,0xbbfa3179,0x3b64361f,0xacb5bbe2,0xb61f3b64,0x3bf12648,0xbb64b61f,0xafd63bff,0x361fbb64,0xbb99b303,0x3b64361f,0x3505bbce,
0xba6db6d7,0x26483b99,0x38c4bb3b,0xbbff3505,0x381d39ed,0x3848bbb6,0xbadd395f,0x3ac23444,0xb0b2bb88,0xbb50393a,0x3beab564,0xb67cba0f,
0xb3c63bfe,0x3be2afd6,0xbbc3aa48,0xb1793bf1,0x3a2fbb0e,0xbbce3444,0x3913378b,0x3303bbb6,0xbbf634a5,0x35c2393a,0x2e46bba8,0xbb773a0f,
0x3913378b,0x389bbbf1,0xba2f3b0e,0x3a8a2fd6,0x2e46bba8,0xbbff3732,0x3bf6b4a5,0x2648bb25,0x36d7381d,0x3732bbce,0xbb3b3add,0x3b25b303,
0x395fbbea,0xbbb6367c,0x39ed30b2,0x3444bb50,0xbb8833c6,0xacb53a8a,0x3564bbc3,0xbbfa389b,0x2a483a6d,0x3bf1b9cb,0xbbfe38c4,0x2fd63984,
0xbbd93aa7,0x3a0fb179,0xb23eb872,0xb93a3be2,0x323e3872,0x3a4fbbff,0xbbd93aa7,0x38ec2648,0x3bd9baa7,0xb732b303,0x323e3872,0x3b25bbce,
0xb23eb872,0xbbb63b50,0x3bd9baa7,0xb444b67c,0x2a48b8c4,0xba8a3bf1,0x3bfeba6d,0xb89b2fd6,0xbb3b381d,0x26483732,0x36d7badd,0xbbff3b25,
0xb9ed3bea,0x3ac2b7e3,0xb95f30b2,0xb8483af6,0x356433c6,0x3b50bbfa,0xbb883bc3,0x367c2cb5,0x3ba8ba2f,0xb5c22cb5,0xb4a53913,0x3b77bbfa,
0x3b0ebbf6,0xba8a38ec,0x378bae46,0x389bba4f,0x34a5b913,0xbbff3b99,0x3ba8ba2f,0x2648b505,0xb78b2e46,0xbac23bb6,0x3b0ebbf6,0xb8483444,
0xb81d395f,0x3bf1bbff,0xbadd39ed,0x2fd6a648,0xb0b23564,0x3b99bbce,0xbbea3b88,0x3505b303,0x33c6aa48,0x3af6bb50,0xbbc33bfe,0x37e3b67c,
0x38c4b6d7,0x3a0fba8a,0xba6d3b3b,0x393ab89b,0xb9a839a8,0xafd62648,0x39a8b9a8,0xbbf13bff,0xb9a839a8,0xb5053303,0x39a8b9a8,0xbb993bce,
0xb9a839a8,0xb7e3367c,0x39a8b9a8,0xbaf63b50,0xb9a839a8,0xb93a389b,0x39a8b9a8,0xba0f3a8a,0x3addb9ed,0xbb773bfa,0x381db95f,0x35c2acb5,
0x3beabb88,0xb89b3a4f,0x30b2b564,0x3a8ab8ec,0x3bc3bbfe,0xa6483505,0xb3c62a48,0x3bffbb99,0x3a6dbb3b,0x3848b444,0xb8c436d7,0x3ac2bbb6,
0x34a5b913,0x389bafd6,0xbba83a2f,0x3a8abbf1,0xb78b2e46,0x3bffbb25,0xbb0e3bf6,0xa648b732,0xbba83a2f,0x3848baf6,0xb4a53913,0xbac237e3,
0xbb0e3bf6,0xb67cacb5,0x378bae46,0xbb503bfa,0xbbfe3a6d,0x393abbe2,0xaa4838c4,0xba0f3179,0xb6d73add,0xb8eca648,0x3b3bb81d,0xba4f3bff,
0x395fb0b2,0xbb253bce,0x39edbbea,0x37323303,0x3b88bbc3,0x3444367c,0xb564b3c6,0x3bb6bb50,0x323e3872,0xbb253303,0x3bd9baa7,0xb7323bce,
0x3bd9baa7,0xb4443b50,0xb23eb872,0x3bb6b67c,0xb23eb872,0x3bfab89b,0xbbd93aa7,0x2cb5ba8a,0xbbd93aa7,0xafd6b984,0x323e3872,0xbbf139cb,
0x3b3bbadd,0xb3033bb6,0xb6d7b81d,0x3bceb444,0xb9edb0b2,0x3b77ba0f,0xb95f3bea,0xb5c2b93a,0xb5643bc3,0xba8aafd6,0x3b88b3c6,0xb89b3bf1,
0x3bfeb8c4,0xa6483b25,0xaa48ba6d,0x3bffb732,0xb913b78b,0x3bffb505,0xba2f3b0e,0xa648bb99,0xae463ba8,0xbac2b444,0x3bf6b4a5,0xb8483bb6,
0x3a2fbb0e,0x367c3a0f,0xb913b78b,0x3b50b93a,0xbbf634a5,0x3179bbf1,0xae463ba8,0xbbe22fd6,0xb8c43b3b,0xb444bb77,0x3a6d36d7,0xbbb635c2,
0x3addb95f,0x2cb53be2,0xb81db9ed,0x3bfab179,0xbbea3564,0x2fd6bbff,0x30b23b88,0xbbf1a648,0x3bc32a48,0xb5053bce,0x33c6bbfe,0x3b993303,
0x3b64361f,0xbaf6367c,0x361fbb64,0x37e33b50,0xbb64b61f,0x3a0fb89b,0xb61f3b64,0xb93aba8a,0x3b64361f,0xb8ec39cb,0x361fbb64,0x3a4f3984,
0xbb64b61f,0x3732bac2,0xb61f3b64,0xbb25b848,0x30b2bb88,0x39843b25,0xbbeab564,0x39cbb732,0x33c63bfe,0xbbceb7e3,0x3bc3aa48,0xb3033af6,
0xb8c4bb3b,0x3b77acb5,0xba6d36d7,0xb5c2bbfa,0x3add395f,0xb89b38ec,0x381db9ed,0x3a8a3a4f,0xbbf6b4a5,0x3848b7e3,0x2e463ba8,0xbac2baf6,
0x3913b78b,0x367c3bfa,0xba2fbb0e,0x3b502cb5,0x2e463ba8,0xbbe2b8ec,0x3bf634a5,0xb1793a4f,0xba2fbb0e,0x3984b505,0xb913378b,0xb9cbbb99,
0x35643bc3,0xbb99bac2,0x3b8833c6,0xb5053848,0xbbfeb8c4,0x37e3b5c2,0xaa483a6d,0xbaf6bb77,0x36d7b81d,0x3a0f3be2,0xbb3bbadd,0x393ab179,
0x395f3bea,0xba4fa648,0x39edb0b2,0x38ec3bff,0x3aa7323e,0xacb5389b,0xb872bbd9,0x3bfa3a8a,0x38723bd9,0xbbf1b984,0x3aa7323e,0x2fd639cb,
0xbaa7b23e,0xb505bac2,0x38723bd9,0xbb99b848,0xb872bbd9,0x3af635c2,0xbaa7b23e,0xb7e3bb77,0xb9edbbea,0x3be23a4f,0xb95fb0b2,0xb179b8ec,
0x3564b3c6,0x39843b99,0xbb88bbc3,0x39cb3505,0x3bfe3a6d,0xb3033444,0xaa48b8c4,0x3bce3bb6,0x36d73add,0xbb77b93a,0x3b3b381d,0x35c23a0f,
0xb78bae46,0xb67cb93a,0x3b0e3bf6,0xbb50ba0f,0xbba8ba2f,0x3179afd6,0x34a53913,0xbbe2bbf1,0xbb0ebbf6,0x39843732,0xb78bae46,0xb9cbbb25,
0xb4a5b913,0x3bce3af6,0xbba8ba2f,0xb303b7e3,0x3bc33bfe,0xba4fb9cb,0x33c62a48,0x38ec3984,0x3a6d3b3b,0xbb25bac2,0x38c436d7,0x37323848,
0x381d395f,0xbbb6bb77,0x3add39ed,0x344435c2,0x30b23564,0xbbfabbe2,0x3bea3b88,0x2cb53179,0x3c003c00,0xafd6a648,0,0xbbf1bbff,
0x3c003c00,0xb505b303,0,0xbb99bbce,0x3c003c00,0xb7e3b67c,0,0xbaf6bb50,0x3c003c00,0xb93ab89b,0,0xba0fba8a,
0xbbc3bbfe,0x35c22cb5,0x33c62a48,0x3b773bfa,0xba6dbb3b,0x3a8a38ec,0x38c436d7,0x389b3a4f,0xb81db95f,0x3bff3b99,0x3add39ed,0x26483505,
0xb0b2b564,0x3ac23bb6,0x3bea3b88,0xb848b444,0x3b0e3bf6,0xb89bafd6,0xb78bae46,0xba8abbf1,0x34a53913,0xbbffbb25,0xbba8ba2f,0x2648b732,
0xb78bae46,0xb848baf6,0xbb0ebbf6,0x3ac237e3,0xbba8ba2f,0x367cacb5,0xb4a5b913,0x3b503bfa,0xb9edbbea,0x3a0f3179,0x395f30b2,0x393a3be2,
0x3564b3c6,0x3a4f3bff,0x3b883bc3,0xb8ec2648,0x3bfe3a6d,0xb7323303,0x2a4838c4,0xbb25bbce,0x36d73add,0xbbb6bb50,0xbb3bb81d,0x3444b67c,
0x38723bd9,0xbb25b303,0xbaa7b23e,0xb732bbce,0xbaa7b23e,0xb444bb50,0xb872bbd9,0x3bb6367c,0xb872bbd9,0x3bfa389b,0x3aa7323e,0x2cb53a8a,
0x3aa7323e,0xafd63984,0x38723bd9,0xbbf1b9cb,0xb564bbc3,0x3bce3444,0x3b8833c6,0x33033bb6,0x3bfe38c4,0xb5c2393a,0xaa483a6d,0xbb77ba0f,
0xb6d7381d,0xb89bbbf1,0xbb3bbadd,0x3a8aafd6,0xb95fbbea,0x3bff3732,0x39edb0b2,0x26483b25,0x2e463ba8,0xbbffb505,0xbbf6b4a5,0x2648bb99,
0xba2fbb0e,0x3ac2b444,0x3913b78b,0x38483bb6,0x3bf634a5,0xb67c3a0f,0x2e463ba8,0xbb50b93a,0xb913378b,0xb179bbf1,0xba2fbb0e,0x3be22fd6,
0x30b2bb88,0x3bb635c2,0x3bea3564,0xb4443b77,0x33c63bfe,0xbbfab179,0xbbc32a48,0x2cb5bbe2,0xb8c4bb3b,0x3bf1a648,0x3a6db6d7,0x2fd63bff,
0x3add395f,0xbb993303,0xb81d39ed,0xb505bbce,0xb61f3b64,0xbaf6b67c,0xbb64b61f,0x37e3bb50,0x361fbb64,0x3a0f389b,0x3b64361f,0xb93a3a8a,
0xb61f3b64,0xb8ecb9cb,0xbb64b61f,0x3a4fb984,0x361fbb64,0x37323ac2,0x3b64361f,0xbb253848,0x38c4bb3b,0x39cb3732,0x3a6d36d7,0xb9843b25,
0xbadd395f,0xb303baf6,0xb81db9ed,0x3bceb7e3,0x3beab564,0xb5c23bfa,0x30b23b88,0xbb77acb5,0xbbc3aa48,0x3a8aba4f,0x33c6bbfe,0x389b38ec,
0xba2f3b0e,0xb848b7e3,0xb913b78b,0x3ac2baf6,0x3bf6b4a5,0xb67c3bfa,0xae463ba8,0xbb502cb5,0xb913b78b,0x3be2b8ec,0x3a2fbb0e,0x31793a4f,
0xae463ba8,0xb984b505,0xbbf634a5,0x39cbbb99,0x3b3bbadd,0x35053848,0x36d7381d,0xbb993ac2,0xb9edb0b2,0x3af6bb77,0x395fbbea,0x37e335c2,
0xb5643bc3,0xb93ab179,0xbb8833c6,0x3a0fbbe2,0x3bfeb8c4,0xb8ec3bff,0x2a483a6d,0xba4f2648,0xbbd93aa7,0xacb5b89b,0xb23eb872,0x3bfaba8a,
0x323e3872,0xbbf13984,0xbbd93aa7,0x2fd6b9cb,0x3bd9baa7,0xb5053ac2,0x323e3872,0xbb993848,0xb23eb872,0x3af6b5c2,0x3bd9baa7,0xb7e33b77,
0x3bfeba6d,0xb17938ec,0xaa4838c4,0xbbe23a4f,0x36d7badd,0x39cbb505,0x3b3bb81d,0xb9843b99,0xb95f30b2,0x3bcebbb6,0x39edbbea,0x33033444,
0xbb883bc3,0x35c2ba0f,0xb564b3c6,0x3b77b93a,0xbba83a2f,0x367cb93a,0x34a5b913,0x3b50ba0f,0xbb0e3bf6,0xb179afd6,0xb78b2e46,0x3be2bbf1,
0xb4a53913,0xb9843732,0xbba83a2f,0x39cbbb25,0x378bae46,0xbbce3af6,0xbb0e3bf6,0x3303b7e3,0x3addb9ed,0xb8ec3984,0xb81d395f,0xba4f39cb,
0x3beabb88,0xb7323848,0xb0b23564,0xbb253ac2,0x3bc3bbfe,0xb44435c2,0x33c6aa48,0xbbb63b77,0x3a6dbb3b,0xacb53179,0x38c4b6d7,0xbbfa3be2,
0xb9a839a8,0x3a4fb9cb,0x39a8b9a8,0x38ecb984,0xb9a839a8,0x3b25bac2,0x39a8b9a8,0x3732b848,0xb9a839a8,0x3bb6bb77,0x39a8b9a8,0x3444b5c2,
0xb9a839a8,0x3bfabbe2,0x39a8b9a8,0x2cb5b179,0x381db95f,0xbb503a0f,0xbadd39ed,0xb67c393a,0x30b2b564,0xbbe23bf1,0xbbea3b88,0x31792fd6,
0xb3c62a48,0xb9cb3b25,0xbbc33bfe,0x3984b732,0xb8c436d7,0xb30337e3,0xba6d3b3b,0x3bcebaf6,0xb4a53913,0x3be2ba4f,0x3ba8ba2f,0x3179b8ec,
0x378bae46,0x3984bb99,0x3b0ebbf6,0xb9cb3505,0x3ba8ba2f,0xb303b444,0x34a5b913,0xbbce3bb6,0x3b0ebbf6,0xbb77393a,0xb78b2e46,0xb5c23a0f,
0x2a48b8c4,0xbbfa3a8a,0xbbfe3a6d,0x2cb5389b,0xbb3b381d,0xafd639cb,0xb6d73add,0x3bf1b984,0xb9ed3bea,0x3b99b848,0x395fb0b2,0x3505bac2,
0x356433c6,0x37e3bb77,0x3b88bbc3,0xbaf635c2,0x323e3872,0x3b99bac2,0x3bd9baa7,0xb505b848,0x3bd9baa7,0xb7e3b5c2,0xb23eb872,0xbaf63b77,
0xb23eb872,0xba0f3be2,0xbbd93aa7,0x393a3179,0xbbd93aa7,0x3a4fa648,0x323e3872,0x38ecbbff,0xb6d7b81d,0xbac23af6,0xbb3b3add,0x384837e3,
0xb95f3bea,0x3b50acb5,0x39ed30b2,0x367cbbfa,0x3b88b3c6,0xb179ba4f,0x3564bbc3,0xbbe238ec,0xaa48ba6d,0xb9cb3b99,0xbbfe38c4,0x39843505,
0x3913378b,0x3984bb25,0x3a2fbb0e,0xb9cbb732,0x2e46bba8,0xbbce37e3,0xbbf634a5,0x33033af6,0xba2f3b0e,0x3b772cb5,0x3913378b,0x35c2bbfa,
0x3bf6b4a5,0xb89bb8ec,0x2e46bba8,0xba8a3a4f,0xba6db6d7,0xb7e33b50,0xb8c43b3b,0x3af6367c,0x381d39ed,0x393aba8a,0x3addb95f,0xba0fb89b,
0xb0b2bb88,0xba4f3984,0xbbea3564,0x38ec39cb,0xb3c63bfe,0x3b25b848,0x3bc32a48,0xb732bac2,0x3b64361f,0x3444bb77,0x361fbb64,0xbbb6b5c2,
0xbb64b61f,0xacb53be2,0xb61f3b64,0x3bfa3179,0x3b64361f,0xafd6bbff,0x361fbb64,0xbbf12648,0xbb64b61f,0x35053bce,0xb61f3b64,0x3b99b303,
0xbbeab564,0xa6483b99,0xb0b23b88,0x3bff3505,0x3bc3aa48,0xb848bbb6,0xb3c6bbfe,0xbac23444,0xba6d36d7,0x3b50393a,0x38c43b3b,0x367cba0f,
0x381db9ed,0xbbe2afd6,0xbaddb95f,0x31793bf1,0x3bf634a5,0xb303bbb6,0xae46bba8,0xbbceb444,0xb913378b,0x3b773a0f,0x3a2f3b0e,0x35c2b93a,
0xae46bba8,0xba8a2fd6,0xbbf6b4a5,0x389b3bf1,0x3a2f3b0e,0xa648bb25,0x3913b78b,0xbbffb732,0xbb88b3c6,0x37323bce,0x35643bc3,0x3b253303,
0x2a48ba6d,0xbbb6b67c,0xbbfeb8c4,0x34443b50,0x3b3b3add,0xacb5ba8a,0x36d7b81d,0xbbfab89b,0xb9ed30b2,0x3bf139cb,0x395f3bea,0x2fd6b984,
0x3aa7323e,0xb93abbe2,0xb872bbd9,0xba0fb179,0x38723bd9,0x38eca648,0x3aa7323e,0xba4fbbff,0xbaa7b23e,0x3b253bce,0x38723bd9,0x3732b303,
0xb872bbd9,0xb444367c,0xbaa7b23e,0x3bb63b50,0xb95fb0b2,0x3a8a3bf1,0x39ed3bea,0x389b2fd6,0xbb88bbc3,0xa6483732,0xb56433c6,0x3bff3b25,
0xaa48b8c4,0xbac2b7e3,0xbbfeba6d,0x38483af6,0x3b3b381d,0xbb50bbfa,0xb6d7badd,0xb67c2cb5,0x378b2e46,0xbb77bbfa,0xbb0ebbf6,0xb5c2acb5,
0x3ba83a2f,0xb89bba4f,0xb4a5b913,0xba8ab8ec,0x3b0e3bf6,0xa648b505,0x378b2e46,0xbbffbb99,0x34a53913,0x38483444,0x3ba83a2f,0xbac2bbb6,
0xb3c6aa48,0x3bf13bff,0x3bc33bfe,0x2fd62648,0xb8c4b6d7,0x3b993bce,0x3a6d3b3b,0x35053303,0xbaddb9ed,0x3af63b50,0x381d395f,0x37e3367c,
0xbbeabb88,0x3a0f3a8a,0x30b23564,0x393a389b,0x3c003c00,0x2fd62648,0,0x3bf13bff,0x3c003c00,0x35053303,0,0x3b993bce,
0x3c003c00,0x37e3367c,0,0x3af63b50,0x3c003c00,0x393a389b,0,0x3a0f3a8a,0xbbc3bbfe,0xb5c2acb5,0x33c62a48,0xbb77bbfa,
0xba6dbb3b,0xba8ab8ec,0x38c436d7,0xb89bba4f,0xb81db95f,0xbbffbb99,0x3add39ed,0xa648b505,0xb0b2b564,0xbac2bbb6,0x3bea3b88,0x38483444,
0x3b0e3bf6,0x389b2fd6,0xb78bae46,0x3a8a3bf1,0x34a53913,0x3bff3b25,0xbba8ba2f,0xa6483732,0xb78bae46,0x38483af6,0xbb0ebbf6,0xbac2b7e3,
0xbba8ba2f,0xb67c2cb5,0xb4a5b913,0xbb50bbfa,0xb9edbbea,0xba0fb179,0x395f30b2,0xb93abbe2,0x3564b3c6,0xba4fbbff,0x3b883bc3,0x38eca648,
0x3bfe3a6d,0x3732b303,0x2a4838c4,0x3b253bce,0x36d73add,0x3bb63b50,0xbb3bb81d,0xb444367c,0x38723bd9,0x3b253303,0xbaa7b23e,0x37323bce,
0xbaa7b23e,0x34443b50,0xb872bbd9,0xbbb6b67c,0xb872bbd9,0xbbfab89b,0x3aa7323e,0xacb5ba8a,0x3aa7323e,0x2fd6b984,0x38723bd9,0x3bf139cb,
0xb564bbc3,0xbbceb444,0x3b8833c6,0xb303bbb6,0x3bfe38c4,0x35c2b93a,0xaa483a6d,0x3b773a0f,0xb6d7381d,0x389b3bf1,0xbb3bbadd,0xba8a2fd6,
0xb95fbbea,0xbbffb732,0x39edb0b2,0xa648bb25,0x2e463ba8,0x3bff3505,0xbbf6b4a5,0xa6483b99,0xba2fbb0e,0xbac23444,0x3913b78b,0xb848bbb6,
0x3bf634a5,0x367cba0f,0x2e463ba8,0x3b50393a,0xb913378b,0x31793bf1,0xba2fbb0e,0xbbe2afd6,0x30b2bb88,0xbbb6b5c2,0x3bea3564,0x3444bb77,
0x33c63bfe,0x3bfa3179,0xbbc32a48,0xacb53be2,0xb8c4bb3b,0xbbf12648,0x3a6db6d7,0xafd6bbff,0x3add395f,0x3b99b303,0xb81d39ed,0x35053bce,
0xb61f3b64,0x3af6367c,0xbb64b61f,0xb7e33b50,0x361fbb64,0xba0fb89b,0x3b64361f,0x393aba8a,0xb61f3b64,0x38ec39cb,0xbb64b61f,0xba4f3984,
0x361fbb64,0xb732bac2,0x3b64361f,0x3b25b848,0x38c4bb3b,0xb9cbb732,0x3a6d36d7,0x3984bb25,0xbadd395f,0x33033af6,0xb81db9ed,0xbbce37e3,
0x3beab564,0x35c2bbfa,0x30b23b88,0x3b772cb5,0xbbc3aa48,0xba8a3a4f,0x33c6bbfe,0xb89bb8ec,0xba2f3b0e,0x384837e3,0xb913b78b,0xbac23af6,
0x3bf6b4a5,0x367cbbfa,0xae463ba8,0x3b50acb5,0xb913b78b,0xbbe238ec,0x3a2fbb0e,0xb179ba4f,0xae463ba8,0x39843505,0xbbf634a5,0xb9cb3b99,
0x3b3bbadd,0xb505b848,0x36d7381d,0x3b99bac2,0xb9edb0b2,0xbaf63b77,0x395fbbea,0xb7e3b5c2,0xb5643bc3,0x393a3179,0xbb8833c6,0xba0f3be2,
0x3bfeb8c4,0x38ecbbff,0x2a483a6d,0x3a4fa648,0xbbd93aa7,0x2cb5389b,0xb23eb872,0xbbfa3a8a,0x323e3872,0x3bf1b984,0xbbd93aa7,0xafd639cb,
0x3bd9baa7,0x3505bac2,0x323e3872,0x3b99b848,0xb23eb872,0xbaf635c2,0x3bd9baa7,0x37e3bb77,0x3bfeba6d,0x3179b8ec,0xaa4838c4,0x3be2ba4f,
0x36d7badd,0xb9cb3505,0x3b3bb81d,0x3984bb99,0xb95f30b2,0xbbce3bb6,0x39edbbea,0xb303b444,0xbb883bc3,0xb5c23a0f,0xb564b3c6,0xbb77393a,
0xbba83a2f,0xb67c393a,0x34a5b913,0xbb503a0f,0xbb0e3bf6,0x31792fd6,0xb78b2e46,0xbbe23bf1,0xb4a53913,0x3984b732,0xbba83a2f,0xb9cb3b25,
0x378bae46,0x3bcebaf6,0xbb0e3bf6,0xb30337e3,0x3addb9ed,0x38ecb984,0xb81d395f,0x3a4fb9cb,0x3beabb88,0x3732b848,0xb0b23564,0x3b25bac2,
0x3bc3bbfe,0x3444b5c2,0x33c6aa48,0x3bb6bb77,0x3a6dbb3b,0x2cb5b179,0x38c4b6d7,0x3bfabbe2,0xb9a839a8,0xba4f39cb,0x39a8b9a8,0xb8ec3984,
0xb9a839a8,0xbb253ac2,0x39a8b9a8,0xb7323848,0xb9a839a8,0xbbb63b77,0x39a8b9a8,0xb44435c2,0xb9a839a8,0xbbfa3be2,0x39a8b9a8,0xacb53179,
0x381db95f,0x3b50ba0f,0xbadd39ed,0x367cb93a,0x30b2b564,0x3be2bbf1,0xbbea3b88,0xb179afd6,0xb3c62a48,0x39cbbb25,0xbbc33bfe,0xb9843732,
0xb8c436d7,0x3303b7e3,0xba6d3b3b,0xbbce3af6,0xb4a53913,0xbbe23a4f,0x3ba8ba2f,0xb17938ec,0x378bae46,0xb9843b99,0x3b0ebbf6,0x39cbb505,
0x3ba8ba2f,0x33033444,0x34a5b913,0x3bcebbb6,0x3b0ebbf6,0x3b77b93a,0xb78b2e46,0x35c2ba0f,0x2a48b8c4,0x3bfaba8a,0xbbfe3a6d,0xacb5b89b,
0xbb3b381d,0x2fd6b9cb,0xb6d73add,0xbbf13984,0xb9ed3bea,0xbb993848,0x395fb0b2,0xb5053ac2,0x356433c6,0xb7e33b77,0x3b88bbc3,0x3af6b5c2,
0x323e3872,0xbb993ac2,0x3bd9baa7,0x35053848,0x3bd9baa7,0x37e335c2,0xb23eb872,0x3af6bb77,0xb23eb872,0x3a0fbbe2,0xbbd93aa7,0xb93ab179,
0xbbd93aa7,0xba4f2648,0x323e3872,0xb8ec3bff,0xb6d7b81d,0x3ac2baf6,0xbb3b3add,0xb848b7e3,0xb95f3bea,0xbb502cb5,0x39ed30b2,0xb67c3bfa,
0x3b88b3c6,0x31793a4f,0x3564bbc3,0x3be2b8ec,0xaa48ba6d,0x39cbbb99,0xbbfe38c4,0xb984b505,0x3913378b,0xb9843b25,0x3a2fbb0e,0x39cb3732,
0x2e46bba8,0x3bceb7e3,0xbbf634a5,0xb303baf6,0xba2f3b0e,0xbb77acb5,0x3913378b,0xb5c23bfa,0x3bf6b4a5,0x389b38ec,0x2e46bba8,0x3a8aba4f,
0xba6db6d7,0x37e3bb50,0xb8c43b3b,0xbaf6b67c,0x381d39ed,0xb93a3a8a,0x3addb95f,0x3a0f389b,0xb0b2bb88,0x3a4fb984,0xbbea3564,0xb8ecb9cb,
0xb3c63bfe,0xbb253848,0x3bc32a48,0x37323ac2,0x3b64361f,0xb4443b77,0x361fbb64,0x3bb635c2,0xbb64b61f,0x2cb5bbe2,0xb61f3b64,0xbbfab179,
0x3b64361f,0x2fd63bff,0x361fbb64,0x3bf1a648,0xbb64b61f,0xb505bbce,0xb61f3b64,0xbb993303,0xbbeab564,0x2648bb99,0xb0b23b88,0xbbffb505,
0x3bc3aa48,0x38483bb6,0xb3c6bbfe,0x3ac2b444,0xba6d36d7,0xbb50b93a,0x38c43b3b,0xb67c3a0f,0x381db9ed,0x3be22fd6,0xbaddb95f,0xb179bbf1,
0x3bf634a5,0x33033bb6,0xae46bba8,0x3bce3444,0xb913378b,0xbb77ba0f,0x3a2f3b0e,0xb5c2393a,0xae46bba8,0x3a8aafd6,0xbbf6b4a5,0xb89bbbf1,
0x3a2f3b0e,0x26483b25,0x3913b78b,0x3bff3732,0xbb88b3c6,0xb732bbce,0x35643bc3,0xbb25b303,0x2a48ba6d,0x3bb6367c,0xbbfeb8c4,0xb444bb50,
0x3b3b3add,0x2cb53a8a,0x36d7b81d,0x3bfa389b,0xb9ed30b2,0xbbf1b9cb,0x395f3bea,0xafd63984,0x3aa7323e,0x393a3be2,0xb872bbd9,0x3a0f3179,
0x38723bd9,0xb8ec2648,0x3aa7323e,0x3a4f3bff,0xbaa7b23e,0xbb25bbce,0x38723bd9,0xb7323303,0xb872bbd9,0x3444b67c,0xbaa7b23e,0xbbb6bb50,
0xb95fb0b2,0xba8abbf1,0x39ed3bea,0xb89bafd6,0xbb88bbc3,0x2648b732,0xb56433c6,0xbbffbb25,0xaa48b8c4,0x3ac237e3,0xbbfeba6d,0xb848baf6,
0x3b3b381d,0x3b503bfa,0xb6d7badd,0x367cacb5,0x378b2e46,0x3b773bfa,0xbb0ebbf6,0x35c22cb5,0x3ba83a2f,0x389b3a4f,0xb4a5b913,0x3a8a38ec,
0x3b0e3bf6,0x26483505,0x378b2e46,0x3bff3b99,0x34a53913,0xb848b444,0x3ba83a2f,0x3ac23bb6,0xb3c6aa48,0xbbf1bbff,0x3bc33bfe,0xafd6a648,
0xb8c4b6d7,0xbb99bbce,0x3a6d3b3b,0xb505b303,0xbaddb9ed,0xbaf6bb50,0x381d395f,0xb7e3b67c,0xbbeabb88,0xba0fba8a,0x30b23564,0xb93ab89b,
0x3c003c00,0xba4fb9cb,0,0xb8ecb984,0x3c003c00,0xbb25bac2,0,0xb732b848,0x3c003c00,0xbbb6bb77,0,0xb444b5c2,
0x3c003c00,0xbbfabbe2,0,0xacb5b179,0x33c62a48,0x367c393a,0x3bc33bfe,0xbb50ba0f,0x38c436d7,0xb1792fd6,0x3a6d3b3b,0xbbe2bbf1,
0x3add39ed,0xb984b732,0x381d395f,0xb9cbbb25,0x3bea3b88,0xbbcebaf6,0x30b23564,0xb303b7e3,0xbb0ebbf6,0x3be23a4f,0x378b2e46,0x317938ec,
0xb4a5b913,0x39843b99,0x3ba83a2f,0xb9cbb505,0x378b2e46,0xb3033444,0x3b0e3bf6,0xbbcebbb6,0x3ba83a2f,0xbb77b93a,0x34a53913,0xb5c2ba0f,
0xb95fb0b2,0x2cb5b89b,0xb9edbbea,0x3bfa3a8a,0xbb88bbc3,0x3bf13984,0x3564b3c6,0x2fd639cb,0xaa48b8c4,0x35053ac2,0x3bfe3a6d,0xbb99b848,
0x3b3b381d,0xbaf6b5c2,0x36d73add,0xb7e3bb77,0x38723bd9,0xbb99bac2,0xbaa7b23e,0x3505b848,0xbaa7b23e,0x37e3b5c2,0xb872bbd9,0x3af63b77,
0xb872bbd9,0x3a0f3be2,0x3aa7323e,0xb93a3179,0x3aa7323e,0xba4fa648,0x38723bd9,0xb8ecbbff,0x3b8833c6,0xb84837e3,0x35643bc3,0xbac2baf6,
0xaa483a6d,0xb67cbbfa,0xbbfeb8c4,0x3b502cb5,0xbb3bbadd,0x3be238ec,0x36d7b81d,0xb1793a4f,0x39edb0b2,0xb9843505,0x395f3bea,0xb9cbbb99,
0xae46bba8,0x39843b25,0x3bf634a5,0xb9cb3732,0x3a2f3b0e,0xbbceb7e3,0xb913378b,0x3303baf6,0xbbf6b4a5,0x3b77acb5,0xae46bba8,0x35c23bfa,
0x3913b78b,0xb89b38ec,0x3a2f3b0e,0xba8aba4f,0xbbeab564,0x3af6b67c,0x30b2bb88,0x37e33b50,0x3bc3aa48,0xba0f389b,0x33c63bfe,0xb93aba8a,
0xba6d36d7,0x38ecb9cb,0xb8c4bb3b,0x3a4f3984,0x381db9ed,0xb7323ac2,0x3add395f,0xbb25b848,0xb61f3b64,0xb444bb77,0xbb64b61f,0x3bb6b5c2,
0x361fbb64,0x2cb53be2,0x3b64361f,0xbbfa3179,0xb61f3b64,0x2fd6bbff,0xbb64b61f,0x3bf12648,0x361fbb64,0xb5053bce,0x3b64361f,0xbb99b303,
0x3a6d36d7,0xbbff3505,0xb8c43b3b,0xa648bb99,0xb81db9ed,0x3ac23444,0x3addb95f,0xb8483bb6,0x30b23b88,0xb67cba0f,0xbbea3564,0x3b50b93a,
0x33c6bbfe,0xb1793bf1,0x3bc32a48,0xbbe22fd6,0x3a2fbb0e,0xb3033bb6,0x3913378b,0xbbce3444,0xbbf634a5,0x3b77ba0f,0x2e46bba8,0x35c2393a,
0x3913378b,0xba8aafd6,0xba2f3b0e,0x389bbbf1,0x2e46bba8,0xa6483b25,0x3bf6b4a5,0xbbff3732,0xb6d7b81d,0x3b25b303,0x3b3bbadd,0xb7323bce,
0xb95f3bea,0x3444bb50,0xb9edb0b2,0x3bb6b67c,0x3b88b3c6,0xbbfa389b,0xb5643bc3,0x2cb5ba8a,0xaa48ba6d,0x2fd63984,0x3bfeb8c4,0xbbf139cb,
0xbbd93aa7,0x393abbe2,0xb23eb872,0x3a0fb179,0x323e3872,0xb8eca648,0xbbd93aa7,0x3a4fbbff,0x3bd9baa7,0xbb253bce,0x323e3872,0xb732b303,
0xb23eb872,0x3444367c,0x3bd9baa7,0xbbb63b50,0xaa4838c4,0xb89b2fd6,0xbbfe3a6d,0x3a8abbf1,0x3b3bb81d,0xbbff3b25,0xb6d73add,0xa648b732,
0x39edbbea,0xb8483af6,0x395fb0b2,0xbac237e3,0xb564b3c6,0x367c2cb5,0x3b88bbc3,0xbb503bfa,0x3ba8ba2f,0xbb773bfa,0xb4a53913,0xb5c22cb5,
0x3b0ebbf6,0xb89b3a4f,0x378bae46,0xba8a38ec,0x34a5b913,0xa6483505,0x3ba8ba2f,0xbbff3b99,0xb78b2e46,0x3848b444,0x3b0ebbf6,0xbac23bb6,
0x381db95f,0x2fd6a648,0x3addb9ed,0xbbf13bff,0x30b2b564,0x3505b303,0x3beabb88,0xbb993bce,0xb3c62a48,0x37e3b67c,0x3bc3bbfe,0xbaf63b50,
0xb8c436d7,0x393ab89b,0x3a6dbb3b,0xba0f3a8a,0xb9a839a8,0x3bf1bbff,0x39a8b9a8,0xafd62648,0xb9a839a8,0x3b99bbce,0x39a8b9a8,0xb5053303,
0xb9a839a8,0x3af6bb50,0x39a8b9a8,0xb7e3367c,0xb9a839a8,0x3a0fba8a,0x39a8b9a8,0xb93a389b,0xbadd39ed,0x35c2acb5,0xb81d395f,0x3b77bbfa,
0xbbea3b88,0x3a8ab8ec,0xb0b23564,0x389bba4f,0xbbc33bfe,0x3bffbb99,0x33c6aa48,0x2648b505,0xba6d3b3b,0x3ac2bbb6,0x38c4b6d7,0xb8483444,
0x34a5b913,0xba8a3bf1,0xbba83a2f,0x389bafd6,0xb78b2e46,0x26483732,0xbb0e3bf6,0x3bffbb25,0xbba83a2f,0x3ac2b7e3,0xb4a53913,0x3848baf6,
0xbb0e3bf6,0x3b50bbfa,0x378bae46,0xb67cacb5,0x3bfeba6d,0xba0f3179,0x2a48b8c4,0xb93a3be2,0x36d7badd,0xba4f3bff,0xbb3b381d,0x38ec2648,
0xb95f30b2,0x37323303,0xb9ed3bea,0x3b25bbce,0xbb883bc3,0x3bb6bb50,0x356433c6,0xb444b67c,0x323e3872,0x3732bbce,0x3bd9baa7,0xbb253303,
0x3bd9baa7,0xbbb6367c,0xb23eb872,0xb4443b50,0xb23eb872,0xacb53a8a,0xbbd93aa7,0x3bfab89b,0xbbd93aa7,0x3bf1b9cb,0x323e3872,0xafd6b984,
0xbb3b3add,0x3bceb444,0x36d7381d,0x3303bbb6,0x39ed30b2,0xb5c2b93a,0x395fbbea,0xbb773a0f,0x3564bbc3,0xb89b3bf1,0xbb8833c6,0x3a8a2fd6,
0xbbfe38c4,0x3bffb732,0x2a483a6d,0x2648bb25,0xb913b78b,0x26483b99,0xba2f3b0e,0x3bffb505,0xae463ba8,0x3848bbb6,0x3bf6b4a5,0xbac2b444,
0x3a2fbb0e,0xbb50393a,0xb913b78b,0x367c3a0f,0xbbf634a5,0x3be2afd6,0xae463ba8,0x3179bbf1,0x38c4bb3b,0xbbb635c2,0xba6db6d7,0x34443b77,
0xbadd395f,0x3bfab179,0x381d39ed,0xacb5bbe2,0x3beab564,0xbbf1a648,0xb0b2bb88,0xafd63bff,0xbbc3aa48,0x3b993303,0xb3c63bfe,0x3505bbce,
0x3b64361f,0xb7e3bb50,0x361fbb64,0xbaf6367c,0xbb64b61f,0x393a3a8a,0xb61f3b64,0x3a0fb89b,0x3b64361f,0xba4fb984,0x361fbb64,0xb8ec39cb,
0xbb64b61f,0x3b253848,0xb61f3b64,0x3732bac2,0xb0b23b88,0x39cbb732,0x3bea3564,0xb984bb25,0xb3c6bbfe,0xb3033af6,0xbbc32a48,0x3bce37e3,
0x38c43b3b,0xb5c2bbfa,0x3a6db6d7,0xbb772cb5,0xbaddb95f,0x3a8a3a4f,0xb81d39ed,0x389bb8ec,0xbbf6b4a5,0x3ac23af6,0x2e463ba8,0x3848b7e3,
0x3913b78b,0xbb50acb5,0xba2fbb0e,0x367c3bfa,0x2e463ba8,0x3179ba4f,0x3bf634a5,0xbbe2b8ec,0xba2fbb0e,0x39cb3b99,0xb913378b,0x3984b505,
0xb564bbc3,0xb5053848,0xbb88b3c6,0x3b993ac2,0x3bfe38c4,0xbaf6bb77,0x2a48ba6d,0xb7e335c2,0xb6d7381d,0x393ab179,0x3b3b3add,0xba0fbbe2,
0xb95fbbea,0x38ec3bff,0xb9ed30b2,0x3a4f2648,0x3aa7323e,0xbbfaba8a,0xb872bbd9,0xacb5389b,0x38723bd9,0xafd6b9cb,0x3aa7323e,0xbbf1b984,
0xbaa7b23e,0x3b993848,0x38723bd9,0xb505bac2,0xb872bbd9,0x37e33b77,0xbaa7b23e,0x3af635c2,0x39ed3bea,0xb179b8ec,0x395f30b2,0xbbe2ba4f,
0xb56433c6,0x39cb3505,0x3b883bc3,0xb984bb99,0xbbfeba6d,0x3bce3bb6,0x2a4838c4,0x3303b444,0xb6d7badd,0x35c23a0f,0xbb3bb81d,0x3b77393a,
0xb78bae46,0x3b503a0f,0x3b0e3bf6,0xb67cb93a,0xbba8ba2f,0x3be23bf1,0x34a53913,0x3179afd6,0xbb0ebbf6,0x39cb3b25,0xb78bae46,0x39843732,
0xb4a5b913,0x330337e3,0xbba8ba2f,0x3bce3af6,0xbbc3bbfe,0x38ec3984,0xb3c6aa48,0x3a4f39cb,0xba6dbb3b,0x37323848,0xb8c4b6d7,0x3b253ac2,
0xb81db95f,0x344435c2,0xbaddb9ed,0x3bb63b77,0xb0b2b564,0x2cb53179,0xbbeabb88,0x3bfa3be2,0x3c003c00,0x3a4f39cb,0,0x38ec3984,
0x3c003c00,0x3b253ac2,0,0x37323848,0x3c003c00,0x3bb63b77,0,0x344435c2,0x3c003c00,0x3bfa3be2,0,0x2cb53179,
0x33c62a48,0xb67cb93a,0x3bc33bfe,0x3b503a0f,0x38c436d7,0x3179afd6,0x3a6d3b3b,0x3be23bf1,0x3add39ed,0x39843732,0x381d395f,0x39cb3b25,
0x3bea3b88,0x3bce3af6,0x30b23564,0x330337e3,0xbb0ebbf6,0xbbe2ba4f,0x378b2e46,0xb179b8ec,0xb4a5b913,0xb984bb99,0x3ba83a2f,0x39cb3505,
0x378b2e46,0x3303b444,0x3b0e3bf6,0x3bce3bb6,0x3ba83a2f,0x3b77393a,0x34a53913,0x35c23a0f,0xb95fb0b2,0xacb5389b,0xb9edbbea,0xbbfaba8a,
0xbb88bbc3,0xbbf1b984,0x3564b3c6,0xafd6b9cb,0xaa48b8c4,0xb505bac2,0x3bfe3a6d,0x3b993848,0x3b3b381d,0x3af635c2,0x36d73add,0x37e33b77,
0x38723bd9,0x3b993ac2,0xbaa7b23e,0xb5053848,0xbaa7b23e,0xb7e335c2,0xb872bbd9,0xbaf6bb77,0xb872bbd9,0xba0fbbe2,0x3aa7323e,0x393ab179,
0x3aa7323e,0x3a4f2648,0x38723bd9,0x38ec3bff,0x3b8833c6,0x3848b7e3,0x35643bc3,0x3ac23af6,0xaa483a6d,0x367c3bfa,0xbbfeb8c4,0xbb50acb5,
0xbb3bbadd,0xbbe2b8ec,0x36d7b81d,0x3179ba4f,0x39edb0b2,0x3984b505,0x395f3bea,0x39cb3b99,0xae46bba8,0xb984bb25,0x3bf634a5,0x39cbb732,
0x3a2f3b0e,0x3bce37e3,0xb913378b,0xb3033af6,0xbbf6b4a5,0xbb772cb5,0xae46bba8,0xb5c2bbfa,0x3913b78b,0x389bb8ec,0x3a2f3b0e,0x3a8a3a4f,
0xbbeab564,0xbaf6367c,0x30b2bb88,0xb7e3bb50,0x3bc3aa48,0x3a0fb89b,0x33c63bfe,0x393a3a8a,0xba6d36d7,0xb8ec39cb,0xb8c4bb3b,0xba4fb984,
0x381db9ed,0x3732bac2,0x3add395f,0x3b253848,0xb61f3b64,0x34443b77,0xbb64b61f,0xbbb635c2,0x361fbb64,0xacb5bbe2,0x3b64361f,0x3bfab179,
0xb61f3b64,0xafd63bff,0xbb64b61f,0xbbf1a648,0x361fbb64,0x3505bbce,0x3b64361f,0x3b993303,0x3a6d36d7,0x3bffb505,0xb8c43b3b,0x26483b99,
0xb81db9ed,0xbac2b444,0x3addb95f,0x3848bbb6,0x30b23b88,0x367c3a0f,0xbbea3564,0xbb50393a,0x33c6bbfe,0x3179bbf1,0x3bc32a48,0x3be2afd6,
0x3a2fbb0e,0x3303bbb6,0x3913378b,0x3bceb444,0xbbf634a5,0xbb773a0f,0x2e46bba8,0xb5c2b93a,0x3913378b,0x3a8a2fd6,0xba2f3b0e,0xb89b3bf1,
0x2e46bba8,0x2648bb25,0x3bf6b4a5,0x3bffb732,0xb6d7b81d,0xbb253303,0x3b3bbadd,0x3732bbce,0xb95f3bea,0xb4443b50,0xb9edb0b2,0xbbb6367c,
0x3b88b3c6,0x3bfab89b,0xb5643bc3,0xacb53a8a,0xaa48ba6d,0xafd6b984,0x3bfeb8c4,0x3bf1b9cb,0xbbd93aa7,0xb93a3be2,0xb23eb872,0xba0f3179,
0x323e3872,0x38ec2648,0xbbd93aa7,0xba4f3bff,0x3bd9baa7,0x3b25bbce,0x323e3872,0x37323303,0xb23eb872,0xb444b67c,0x3bd9baa7,0x3bb6bb50,
0xaa4838c4,0x389bafd6,0xbbfe3a6d,0xba8a3bf1,0x3b3bb81d,0x3bffbb25,0xb6d73add,0x26483732,0x39edbbea,0x3848baf6,0x395fb0b2,0x3ac2b7e3,
0xb564b3c6,0xb67cacb5,0x3b88bbc3,0x3b50bbfa,0x3ba8ba2f,0x3b77bbfa,0xb4a53913,0x35c2acb5,0x3b0ebbf6,0x389bba4f,0x378bae46,0x3a8ab8ec,
0x34a5b913,0x2648b505,0x3ba8ba2f,0x3bffbb99,0xb78b2e46,0xb8483444,0x3b0ebbf6,0x3ac2bbb6,0x381db95f,0xafd62648,0x3addb9ed,0x3bf1bbff,
0x30b2b564,0xb5053303,0x3beabb88,0x3b99bbce,0xb3c62a48,0xb7e3367c,0x3bc3bbfe,0x3af6bb50,0xb8c436d7,0xb93a389b,0x3a6dbb3b,0x3a0fba8a,
0xb9a839a8,0xbbf13bff,0x39a8b9a8,0x2fd6a648,0xb9a839a8,0xbb993bce,0x39a8b9a8,0x3505b303,0xb9a839a8,0xbaf63b50,0x39a8b9a8,0x37e3b67c,
0xb9a839a8,0xba0f3a8a,0x39a8b9a8,0x393ab89b,0xbadd39ed,0xb5c22cb5,0xb81d395f,0xbb773bfa,0xbbea3b88,0xba8a38ec,0xb0b23564,0xb89b3a4f,
0xbbc33bfe,0xbbff3b99,0x33c6aa48,0xa6483505,0xba6d3b3b,0xbac23bb6,0x38c4b6d7,0x3848b444,0x34a5b913,0x3a8abbf1,0xbba83a2f,0xb89b2fd6,
0xb78b2e46,0xa648b732,0xbb0e3bf6,0xbbff3b25,0xbba83a2f,0xbac237e3,0xb4a53913,0xb8483af6,0xbb0e3bf6,0xbb503bfa,0x378bae46,0x367c2cb5,
0x3bfeba6d,0x3a0fb179,0x2a48b8c4,0x393abbe2,0x36d7badd,0x3a4fbbff,0xbb3b381d,0xb8eca648,0xb95f30b2,0xb732b303,0xb9ed3bea,0xbb253bce,
0xbb883bc3,0xbbb63b50,0x356433c6,0x3444367c,0x323e3872,0xb7323bce,0x3bd9baa7,0x3b25b303,0x3bd9baa7,0x3bb6b67c,0xb23eb872,0x3444bb50,
0xb23eb872,0x2cb5ba8a,0xbbd93aa7,0xbbfa389b,0xbbd93aa7,0xbbf139cb,0x323e3872,0x2fd63984,0xbb3b3add,0xbbce3444,0x36d7381d,0xb3033bb6,
0x39ed30b2,0x35c2393a,0x395fbbea,0x3b77ba0f,0x3564bbc3,0x389bbbf1,0xbb8833c6,0xba8aafd6,0xbbfe38c4,0xbbff3732,0x2a483a6d,0xa6483b25,
0xb913b78b,0xa648bb99,0xba2f3b0e,0xbbff3505,0xae463ba8,0xb8483bb6,0x3bf6b4a5,0x3ac23444,0x3a2fbb0e,0x3b50b93a,0xb913b78b,0xb67cba0f,
0xbbf634a5,0xbbe22fd6,0xae463ba8,0xb1793bf1,0x38c4bb3b,0x3bb6b5c2,0xba6db6d7,0xb444bb77,0xbadd395f,0xbbfa3179,0x381d39ed,0x2cb53be2,
0x3beab564,0x3bf12648,0xb0b2bb88,0x2fd6bbff,0xbbc3aa48,0xbb99b303,0xb3c63bfe,0xb5053bce,0x3b64361f,0x37e33b50,0x361fbb64,0x3af6b67c,
0xbb64b61f,0xb93aba8a,0xb61f3b64,0xba0f389b,0x3b64361f,0x3a4f3984,0x361fbb64,0x38ecb9cb,0xbb64b61f,0xbb25b848,0xb61f3b64,0xb7323ac2,
0xb0b23b88,0xb9cb3732,0x3bea3564,0x39843b25,0xb3c6bbfe,0x3303baf6,0xbbc32a48,0xbbceb7e3,0x38c43b3b,0x35c23bfa,0x3a6db6d7,0x3b77acb5,
0xbaddb95f,0xba8aba4f,0xb81d39ed,0xb89b38ec,0xbbf6b4a5,0xbac2baf6,0x2e463ba8,0xb84837e3,0x3913b78b,0x3b502cb5,0xba2fbb0e,0xb67cbbfa,
0x2e463ba8,0xb1793a4f,0x3bf634a5,0x3be238ec,0xba2fbb0e,0xb9cbbb99,0xb913378b,0xb9843505,0xb564bbc3,0x3505b848,0xbb88b3c6,0xbb99bac2,
0x3bfe38c4,0x3af63b77,0x2a48ba6d,0x37e3b5c2,0xb6d7381d,0xb93a3179,0x3b3b3add,0x3a0f3be2,0xb95fbbea,0xb8ecbbff,0xb9ed30b2,0xba4fa648,
0x3aa7323e,0x3bfa3a8a,0xb872bbd9,0x2cb5b89b,0x38723bd9,0x2fd639cb,0x3aa7323e,0x3bf13984,0xbaa7b23e,0xbb99b848,0x38723bd9,0x35053ac2,
0xb872bbd9,0xb7e3bb77,0xbaa7b23e,0xbaf6b5c2,0x39ed3bea,0x317938ec,0x395f30b2,0x3be23a4f,0xb56433c6,0xb9cbb505,0x3b883bc3,0x39843b99,
0xbbfeba6d,0xbbcebbb6,0x2a4838c4,0xb3033444,0xb6d7badd,0xb5c2ba0f,0xbb3bb81d,0xbb77b93a,0xb78bae46,0xbb50ba0f,0x3b0e3bf6,0x367c393a,
0xbba8ba2f,0xbbe2bbf1,0x34a53913,0xb1792fd6,0xbb0ebbf6,0xb9cbbb25,0xb78bae46,0xb984b732,0xb4a5b913,0xb303b7e3,0xbba8ba2f,0xbbcebaf6,
0xbbc3bbfe,0xb8ecb984,0xb3c6aa48,0xba4fb9cb,0xba6dbb3b,0xb732b848,0xb8c4b6d7,0xbb25bac2,0xb81db95f,0xb444b5c2,0xbaddb9ed,0xbbb6bb77,
0xb0b2b564,0xacb5b179,0xbbeabb88,0xbbfabbe2,0x3c003c00,0x96480000,0x3c003c00,0xa311a248,0x3c003c00,0x9cb69a48,0x3c003c00,0xa452a3db,
0x3c003c00,0x9fdb9e48,0x3c003c00,0xa51ba4b6,0x3c003c00,0xa17fa0b6,0x3bff3c00,0xa5e4a57f,0x3c003c00,0x9fdb0000,0x3bfb3bfc,0xac6aabd9,
0x3bff3c00,0xa5e4a3db,0x3bf93bfa,0xad65ace7,0x3bfe3bff,0xa8e8a7da,0x3bf63bf7,0xae5fade2,0x3bfd3bfe,0xaadea9e3,0x3bf23bf4,0xaf59aedc,
0x3c003c00,0xa3110000,0x3bf03bf4,0xafefaf0e,0x3bfe3bff,0xa94da711,0x3be83bed,0xb0d7b067,0x3bfb3bfd,0xac6aab11,0x3bdf3be4,0xb1b6b147,
0x3bf63bf9,0xae2dad4c,0x3bd43bda,0xb294b226,0x3c003c00,0xa51b0000,0x3bdf3be6,0xb1b6b115,0x3bfc3bfe,0xaba7a91b,0x3bcf3bd7,0xb2f7b257,
0x3bf63bf9,0xae5fad1a,0x3bbc3bc6,0xb41ab396,0x3bec3bf1,0xb074afa4,0x3ba53bb1,0xb4b7b469,0x3bff3c00,0xa6ad0000,0x3bc83bd4,0xb371b2a1,
0x3bfa3bfd,0xad00aaac,0x3bac3bbb,0xb487b420,0x3bef3bf5,0xb029aeaa,0x3b8b3b9d,0xb552b4ed,0x3bde3be7,0xb1cfb0fd,0x3b653b79,0xb61ab5b6,
0x3bff3c00,0xa81f0000,0x3bab3bbc,0xb493b414,0x3bf63bfc,0xae2dac1f,0x3b813b97,0xb58db511,0x3be53bef,0xb122b01d,0x3b4f3b69,0xb682b608,
0x3bcc3bda,0xb328b226,0x3b163b33,0xb76fb6f9,0x3bfe3c00,0xa8e80000,0x3b873ba0,0xb56ab4d5,0x3bf23bfa,0xaf59ace7,0x3b4c3b6b,0xb68db5fd,
0x3bda3be8,0xb219b0e4,0x3b073b2b,0xb7a6b71b,0x3bb73bca,0xb43eb34c,0x3ab63ae0,0xb85ab817,0x3bfe3c00,0xa9b10000,0x3b5e3b80,0xb63cb593,
0x3bee3bf8,0xb042adb0,0x3b103b39,0xb785b6e3,0x3bce3be0,0xb30fb1aa,0x3ab33ae3,0xb85fb812,0x3b9e3bb7,0xb4e7b438,0x3a493a7f,0xb8f3b8ab,
0x3bfd3c00,0xaa7a0000,0x3b2f3b5a,0xb70ab64e,0x3be83bf6,0xb0d7ae78,0x3acb3aff,0xb83ab7c2,0x3bbf3bd6,0xb402b26f,0x3a543a92,0xb8e5b891,
0x3b813ba2,0xb58db4c9,0x39cd3a13,0xb982b935,0x3bfd3c00,0xab430000,0x3afb3b30,0xb7d2b705,0x3be23bf3,0xb16caf40,0x3a7e3abf,0xb8adb84d,
0x3bae3bcb,0xb47bb334,0x39eb3a37,0xb962b909,0x3b603b8a,0xb631b558,0x3946399b,0xba04b9b5,0x3bfc3c00,0xac060000,0x3ac13b02,0xb84ab7b7,
0x3bdc3bf0,0xb201b004,0x3a293a78,0xb91bb8b5,0x3b9c3bc0,0xb4f3b3f7,0x397939d4,0xb9d6b97b,0x3b3d3b70,0xb6d2b5e5,0x38b23918,0xba7aba2b,
0x3bfb3c00,0xac6a0000,0x3a813ad0,0xb8a8b832,0x3bd43bed,0xb294b067,0x39cd3a2b,0xb982b918,0x3b873bb2,0xb56ab45d,0x38fd3969,0xba41b9e5,
0x3b163b53,0xb76fb670,0x3815388c,0xbae1ba95,0x3bfa3c00,0xacce0000,0x3a3d3a99,0xb902b887,0x3bcc3be9,0xb328b0cb,0x396b39d8,0xb9e3b976,
0x3b713ba4,0xb5dfb4bd,0x387a38f6,0xbaa2ba47,0x3aeb3b33,0xb805b6f9,0x36dd37ee,0xbb3abaf3,0x3bf93c00,0xad330000,0x39f43a5e,0xb958b8d8,
0x3bc33be5,0xb3bab12e,0x39023980,0xba3db9d0,0x3b593b95,0xb654b51d,0x37dd387c,0xbaf7baa0,0x3abd3b11,0xb850b780,0x358136b5,0xbb83bb43,
0x3bf83c00,0xad970000,0x39a63a1f,0xb9aab927,0x3bba3be1,0xb426b191,0x38943922,0xba90ba23,0x3b3f3b84,0xb6c6b57c,0x36bb37f9,0xbb42baf0,
0x3a8c3aed,0xb899b802,0x341a3570,0xbbbcbb86,0x3bf73c00,0xadfb0000,0x395439dc,0xb9f8b972,0x3bb03bdc,0xb46fb1f4,0x382038bf,0xbadbba71,
0x3b243b72,0xb737b5da,0x358d36ee,0xbb81bb36,0x3a583ac6,0xb8e0b842,0x31533420,0xbbe3bbbb,0x3bf63c00,0xae5f0000,0x38fd3996,0xba41b9ba,
0x3ba53bd7,0xb4b7b257,0x374e3858,0xbb1ebab8,0x3b073b5f,0xb7a6b637,0x345735da,0xbbb3bb72,0x3a213a9c,0xb924b881,0x2cce3191,0xbbfabbe1,
0x3bf53c00,0xaec30000,0x38a3394d,0xba85b9fe,0x3b9a3bd2,0xb4ffb2b9,0x365437d8,0xbb59baf9,0x3ae83b4b,0xb80ab693,0x323234bd,0xbbd9bba4,
0x39e73a71,0xb966b8bf,0xa4522db0,0xbc00bbf8,0x3bf33c00,0xaf270000,0x38453900,0xbac4ba3f,0x3b8e3bcd,0xb546b31b,0x355236f9,0xbb8bbb33,
0x3ac73b36,0xb840b6ee,0x2f593334,0xbbf2bbcb,0x39aa3a43,0xb9a6b8fb,0xaef51a48,0xbbf4bc00,0x3bf23c00,0xaf8b0000,0x37c838b0,0xbafeba7c,
0x3b813bc7,0xb58db37d,0x344b3614,0xbbb5bb67,0x3aa53b20,0xb874b748,0x288430e4,0xbbffbbe8,0x396b3a13,0xb9e3b935,0xb263ad4c,0xbbd7bbf9,
0x3bf03c00,0xafef0000,0x36ff385d,0xbb32bab5,0x3b733bc1,0xb5d4b3df,0x327c3529,0xbbd6bb93,0x3a813b08,0xb8a8b7a1,0xa9b12d1a,0xbbfebbf9,
0x392939e1,0xba1db96d,0xb49fb160,0xbba9bbe3,0x3bef3c00,0xb0290000,0x36313807,0xbb60bae9,0x3b653bbb,0xb61ab420,0x305b3438,0xbbedbbb7,
0x3a5c3af0,0xb8dbb7f9,0xafef1e48,0xbbf0bc00,0x38e539ad,0xba54b9a4,0xb602b408,0xbb6abbbe,0x3bed3c00,0xb05b0000,0x355e375e,0xbb89bb1a,
0x3b573bb4,0xb65fb451,0x2c6a3288,0xbbfbbbd5,0x3a353ad6,0xb90cb828,0xb27cac51,0xbbd6bbfb,0x389e3976,0xba89b9d8,0xb759b558,0xbb1bbb8a,
0x3beb3c00,0xb08d0000,0x348736aa,0xbbacbb46,0x3b473bad,0xb6a4b481,0x16483099,0xbc00bbeb,0x3a0d3abc,0xb93cb852,0xb47bb080,0xbbaebbec,
0x3855393e,0xbababa0b,0xb850b69e,0xbabdbb49,0x3be93c00,0xb0be0000,0x335935f1,0xbbc9bb6e,0x3b373ba6,0xb6e8b4b1,0xac382d4c,0xbbfcbbf9,
0x39e33aa0,0xb96bb87c,0xb5b1b2d2,0xbb7abbd1,0x380a3905,0xbae8ba3b,0xb8eab7d8,0xba50baf9,0x3be73c00,0xb0f00000,0x319e3534,0xbbe0bb91,
0x3b273b9e,0xb72cb4e1,0xb042257f,0xbbeebc00,0x39b83a83,0xb999b8a6,0xb6ddb48d,0xbb3abbab,0x377a38c9,0xbb13ba69,0xb979b881,0xb9d6ba9c,
0x3be53c00,0xb1220000,0x2fbd3475,0xbbf1bbaf,0x3b163b97,0xb76fb511,0xb263a91b,0xbbd7bbfe,0x398b3a65,0xb9c5b8ce,0xb7feb5ab,0xbaeebb7b,
0x36dd388c,0xbb3aba95,0xb9fcb90e,0xb94fba33,0x3be33c00,0xb1530000,0x2c383365,0xbbfcbbc9,0x3b043b8f,0xb7b2b540,0xb43eae78,0xbbb7bbf6,
0x395d3a47,0xb9f0b8f6,0xb889b6c1,0xba97bb41,0x363c384d,0xbb5ebabf,0xba73b992,0xb8bcb9be,0x3be13c00,0xb1850000,0x217f31db,0xbc00bbdd,
0x3af13b86,0xb7f3b570,0xb546b12e,0xbb8ebbe5,0x392e3a27,0xba19b91d,0xb90cb7cd,0xba35bafc,0x3599380d,0xbb7fbae6,0xbadbba0b,0xb820b93e,
0x3bdf3c00,0xb1b60000,0xa9b1304e,0xbbfebbed,0x3ade3b7d,0xb81ab59f,0xb648b31b,0xbb5cbbcd,0x38fd3a07,0xba41b943,0xb986b867,0xb9c9baae,
0x34f33796,0xbb9cbb0b,0xbb35ba78,0xb6f4b8b5,0x3bdd3c00,0xb1e80000,0xae5f2d7e,0xbbf6bbf8,0x3acb3b74,0xb83ab5ce,0xb742b481,0xbb21bbad,
0x38cc39e5,0xba67b969,0xb9f8b8e2,0xb954ba56,0x344b3710,0xbbb5bb2e,0xbb7fbad9,0xb599b822,0x3bda3c00,0xb2190000,0xb0f028b6,0xbbe7bbff,
0x3ab63b6b,0xb85ab5fd,0xb81ab570,0xbadebb86,0x389939c3,0xba8cb98d,0xba60b956,0xb8d6b9f6,0x33403687,0xbbcbbb4e,0xbbb8bb2e,0xb432b710,
0x3bff3bff,0xa6ada648,0x3bfe3bff,0xa8e8a8b6,0x3bff3bff,0xa776a711,0x3bfe3bfe,0xa94da91b,0x3bff3bff,0xa81fa7da,0x3bfe3bfe,0xa9b1a97f,
0x3bff3bff,0xa884a852,0x3bfe3bfe,0xaa16a9e3,0x3bef3bf1,0xb029afd6,0x3bda3bdd,0xb219b1db,0x3bea3bed,0xb0a6b067,0x3bd43bd7,0xb294b257,
0x3be53be8,0xb122b0e4,0x3bce3bd1,0xb30fb2d2,0x3be03be3,0xb19eb160,0x3bc63bca,0xb389b34c,0x3bc83bce,0xb371b303,0x3b873b91,0xb56ab534,
0x3bba3bc1,0xb426b3df,0x3b733b7d,0xb5d4b59f,0x3bab3bb2,0xb493b45d,0x3b5e3b69,0xb63cb608,0x3b9a3ba2,0xb4ffb4c9,0x3b473b53,0xb6a4b670,
0x3b8b3b99,0xb552b505,0x3b073b1a,0xb7a6b75e,0x3b6f3b7d,0xb5ebb59f,0x3ade3af3,0xb81ab7ee,0x3b4f3b5f,0xb682b637,0x3ab33ac9,0xb85fb83d,
0x3b2c3b3e,0xb715b6cc,0x3a853a9c,0xb8a3b881,0x3b3a3b50,0xb6ddb67c,0x3a5c3a7c,0xb8dbb8b0,0x3b0a3b22,0xb79bb73d,0x3a193a3b,0xb92eb905,
0x3ad53af0,0xb82ab7f9,0x39d239f6,0xb97db956,0x3a9b3ab8,0xb884b858,0x398639ad,0xb9c9b9a4,0x3ad53af6,0xb82ab7e3,0x398b39ba,0xb9c5b996,
0x3a8c3ab1,0xb899b862,0x3929395b,0xba1db9f2,0x3a3d3a65,0xb902b8ce,0x38c138f6,0xba6fba47,0x39e73a13,0xb966b935,0x3855388c,0xbababa95,
0x3a5c3a8a,0xb8dbb89b,0x389938d8,0xba8cba5e,0x39f83a2b,0xb954b918,0x38153858,0xbae1bab8,0x398b39c3,0xb9c5b98d,0x371537a1,0xbb2cbb08,
0x39163951,0xba2db9fa,0x35f73687,0xbb6cbb4e,0x39d23a0f,0xb97db93a,0x371537b7,0xbb2cbb02,0x394f3992,0xb9fcb9be,0x35c83670,0xbb76bb53,
0x38c13909,0xba6fba37,0x346f351d,0xbbb0bb95,0x382a3877,0xbad5baa3,0x3219337d,0xbbdabbc7,0x39373984,0xba11b9cb,0x34cf3593,0xbba1bb80,
0x389438e7,0xba90ba52,0x327c3408,0xbbd6bbbe,0x37c8383d,0xbafebac9,0x2e9130e4,0xbbf5bbe8,0x36543710,0xbb59bb2e,0x16482aac,0xbc00bbfd,
0x388e38ec,0xba93ba4f,0x30d732a1,0xbbe8bbd4,0x3790382d,0xbb0dbad3,0x28e82e14,0xbbfebbf7,0x35eb36c1,0xbb6fbb41,0xaccea4b6,0xbbfabc00,
0x34323511,0xbbb8bb97,0xb201b036,0xbbdcbbee,0x37b23848,0xbb04bac2,0x96482bd9,0xbc00bbfc,0x35df36cc,0xbb71bb3e,0xb010ac1f,0xbbefbbfc,
0x33eb34ed,0xbbc0bb9d,0xb402b20d,0xbbbfbbdb,0x2fef31f4,0xbbf0bbdc,0xb5ebb4f9,0xbb6fbb9b,0x36313732,0xbb60bb25,0xb0f0ad7e,0xbbe7bbf8,
0x341a3529,0xbbbcbb93,0xb49fb31b,0xbba9bbcd,0x2fbd320d,0xbbf1bbdb,0xb6afb5ab,0xbb45bb7b,0xa4522aac,0xbc00bbfd,0xb850b7ac,0xbabdbb05,
0x349f35c2,0xbba9bb77,0xb4dbb365,0xbb9fbbc9,0x308d32ea,0xbbebbbd0,0xb715b5fd,0xbb2cbb6b,0x9fdb2c51,0xbc00bbfb,0xb894b812,0xba90bae3,
0xb109ad4c,0xbbe6bbf9,0xb982b90e,0xb9cdba33,0x32013444,0xbbdcbbb6,0xb721b5f1,0xbb2abb6e,0x26ad2edc,0xbbffbbf4,0xb8adb822,0xba7ebad9,
0xb05bab11,0xbbedbbfd,0xb9aab930,0xb9a6ba17,0xb4b7b2ea,0xbba5bbd0,0xba81ba1b,0xb8a8b92b,0x2d653179,0xbbf9bbe2,0xb89eb807,0xba89bae9,
0xadc99a48,0xbbf8bc00,0xb9afb92b,0xb9a1ba1b,0xb432b1aa,0xbbb8bbe0,0xba93ba27,0xb88eb91d,0xb6d2b587,0xbb3dbb82,0xbb45baf3,0xb6afb7ee,
0xa51b2cb5,0xbc00bbfa,0xb990b900,0xb9c0ba3f,0xb294af40,0xbbd4bbf3,0xba89ba13,0xb89eb935,0xb625b4bd,0xbb63bba4,0xbb47baf0,0xb6a4b7f9,
0xb865b780,0xbab0bb11,0xbbc5bb8f,0xb3a2b540,0xafefa648,0xbbf0bbff,0xba60b9dc,0xb8d6b972,0xb517b31b,0xbb96bbcd,0xbb35bad3,0xb6f4b82d,
0xb7feb693,0xbaeebb4b,0xbbc0bb84,0xb3ebb57c,0xb94ab8ab,0xba00ba7f,0xbbfdbbe9,0xaa7ab0cb,0xb340afd6,0xbbcbbbf1,0xbb0aba99,0xb79bb887,
0xb6d2b540,0xbb3dbb8f,0xbbaebb67,0xb47bb614,0xb8dbb828,0xba5cbad6,0xbbfbbbe0,0xac9cb1aa,0xba15b980,0xb933b9d0,0xbbecbbff,0x30742852,
0xb53ab303,0xbb90bbce,0xbb89bb30,0xb55eb705,0xb83ab6e3,0xbacbbb39,0xbbf2bbca,0xaf8bb34c,0xb9a1b8f6,0xb9afba47,0xbbf5bc00,0x2ec39e48,
0xbac1ba3b,0xb84ab905,0xbb92bbd0,0x352f32ea,0xb6c6b505,0xbb3fbb99,0xbbdcbba0,0xb201b4d5,0xb8fdb838,0xba41bacc,0xbbfebbfb,0x2a16ac83,
0xba50b9b1,0xb8eab99f,0xbbaebbe4,0x347b3147,0xbb4abad9,0xb699b822,0xbaf1bb5d,0x37f33642,0xb820b67c,0xbadbbb50,0xbbffbbe6,0xa884b115,
0xb9afb8f1,0xb9a1ba4b,0xbbd2bbf8,0x32c62db0,0xbae5ba56,0xb80fb8e2,0xbb2abb8c,0x3721354c,0xbbaebb58,0xb47bb659,0xba11baaa,0x3937386d,
0xb8d1b7e3,0xba64baf6,0xbbf2bc00,0x2f8ba248,0xba4db99b,0xb8eeb9b5,0xbb6fbbc1,0x35eb33df,0xbb5cbae3,0xb648b812,0xba6bbafc,0x38c737cd,
0xbbebbbb4,0xb08db451,0xb8f8b9be,0x3a453992,0xb974b89b,0xb9daba8a,0xbbb5bbed,0x344b304e,0xbad5ba33,0xb82ab90e,0xbad8bb58,0x38253659,
0xbbb3bb55,0xb457b665,0xb979ba37,0x39d63909,0xbc00bbed,0x9648b067,0xb764b8a0,0x3b183a87,0xba09b93a,0xb941ba0f,0xbb4abbaf,0x36993475,
0xbb45bab8,0xb6afb858,0xba11babf,0x3937384d,0xbbeabbab,0xb0a6b48d,0xb85ab943,0x3ab63a07,0xbbecbc00,0x30749a48,0xb493b6b5,0x3bab3b43,
0xba8cb9cb,0xb899b984,0xbab3bb46,0x385f36aa,0xbb9cbb28,0xb4f3b726,0xb91fb9fa,0x3a253951,0xbc00bbe4,0xa452b147,0xb631b828,0x3b603ad6,
0xbbb0bbee,0x346f3036,0xae5fb3df,0x3bf63bc1,0xbafeba4f,0xb7c8b8ec,0xb9f4bab5,0x3958385d,0xbbd8bb82,0xb24bb587,0xb80ab90e,0x3ae83a33,
0xbbf3bbfe,0x2f27a97f,0xb2f7b5da,0x3bcf3b72,0xbb4cbbb7,0x368d3438,0x2dc9ac1f,0x3bf83bfc,0xbb5cbac2,0xb648b848,0xb911b9fe,0x3a31394d,
0xbbf9bbc4,0xad33b3ae,0xb5b1b802,0x3b7a3aed,0xbbc5bbf9,0x33a22d1a,0xa94db26f,0x3bfe3bd6,0xbac4bb5d,0x38453642,0x346f2fa4,0x3bb03bf1,
0xbba5bb25,0xb4b7b732,0xb80fb927,0x3ae53a1f,0xbbffbbee,0x2884b036,0xb24bb5b6,0x3bd83b79,0xbb76bbd6,0x35c8326f,0x305ba7da,0x3bed3bff,
0xba19bae0,0x392e3817,0x374234c9,0x3b213ba2,0xbbd9bb77,0xb232b5c2,0xb5ebb832,0x3b6f3ad0,0xbbe8bc00,0x30d7a57f,0xa81fb288,0x3bff3bd5,
0xbb07bb95,0x37a6351d,0x34f33080,0x3b9c3bec,0xb94fba43,0x39fc38fb,0x38ea3780,0x3a503b11,0xbbf8bbb6,0xadc9b444,0xb328b64e,0x3bcc3b5a,
0xbbb7bbf8,0x343e2db0,0x3042a9e3,0x3bee3bfe,0xba7abb36,0x38b236ee,0x379034ed,0x3b0d3b9d,0xb86ab989,0x3aac39c7,0x3a0438fb,0x39463a43,
0xbc00bbe2,0x2311b179,0xac9cb414,0x3bfb3bbc,0xbb6abbd7,0x36023257,0x34b72f40,0x3ba53bf3,0xb9d2babc,0x397d3852,0x38f83775,0x3a453b14,
0xb6ddb8b5,0x3b3a3a78,0x3ae83a0b,0x380a393e,0xbbf2bbfa,0x2f8bacb5,0x2d33af0e,0x3bf93bf4,0xbb04bb9e,0x37b234e1,0x372c3451,0x3b273bb4,
0xb911ba27,0x3a31391d,0x3a0038e2,0x394a3a56,0xb4c3b796,0x3ba33b0b,0x3b8b3ae6,0x3552380d,0x4c004c00,0x26480000,0x4c004c00,0x33113248,
0x4c004c00,0x2cb62a48,0x4c004c00,0x345233db,0x4c004c00,0x2fdb2e48,0x4c004c00,0x351b34b6,0x4c004c00,0x317f30b6,0x4bff4c00,0x35e4357f,
0x4c004c00,0x2fdb0000,0x4bfb4bfc,0x3c6a3bd9,0x4bff4c00,0x35e433db,0x4bf94bfa,0x3d653ce7,0x4bfe4bff,0x38e837da,0x4bf64bf7,0x3e5f3de2,
0x4bfd4bfe,0x3ade39e3,0x4bf24bf4,0x3f593edc,0x4c004c00,0x33110000,0x4bf04bf4,0x3fef3f0e,0x4bfe4bff,0x394d3711,0x4be84bed,0x40d74067,
0x4bfb4bfd,0x3c6a3b11,0x4bdf4be4,0x41b64147,0x4bf64bf9,0x3e2d3d4c,0x4bd44bda,0x42944226,0x4c004c00,0x351b0000,0x4bdf4be6,0x41b64115,
0x4bfc4bfe,0x3ba7391b,0x4bcf4bd7,0x42f74257,0x4bf64bf9,0x3e5f3d1a,0x4bbc4bc6,0x441a4396,0x4bec4bf1,0x40743fa4,0x4ba54bb1,0x44b74469,
0x4bff4c00,0x36ad0000,0x4bc84bd4,0x437142a1,0x4bfa4bfd,0x3d003aac,0x4bac4bbb,0x44874420,0x4bef4bf5,0x40293eaa,0x4b8b4b9d,0x455244ed,
0x4bde4be7,0x41cf40fd,0x4b654b79,0x461a45b6,0x4bff4c00,0x381f0000,0x4bab4bbc,0x44934414,0x4bf64bfc,0x3e2d3c1f,0x4b814b97,0x458d4511,
0x4be54bef,0x4122401d,0x4b4f4b69,0x46824608,0x4bcc4bda,0x43284226,0x4b164b33,0x476f46f9,0x4bfe4c00,0x38e80000,0x4b874ba0,0x456a44d5,
0x4bf24bfa,0x3f593ce7,0x4b4c4b6b,0x468d45fd,0x4bda4be8,0x421940e4,0x4b074b2b,0x47a6471b,0x4bb74bca,0x443e434c,0x4ab64ae0,0x485a4817,
0x4bfe4c00,0x39b10000,0x4b5e4b80,0x463c4593,0x4bee4bf8,0x40423db0,0x4b104b39,0x478546e3,0x4bce4be0,0x430f41aa,0x4ab34ae3,0x485f4812,
0x4b9e4bb7,0x44e74438,0x4a494a7f,0x48f348ab,0x4bfd4c00,0x3a7a0000,0x4b2f4b5a,0x470a464e,0x4be84bf6,0x40d73e78,0x4acb4aff,0x483a47c2,
0x4bbf4bd6,0x4402426f,0x4a544a92,0x48e54891,0x4b814ba2,0x458d44c9,0x49cd4a13,0x49824935,0x4bfd4c00,0x3b430000,0x4afb4b30,0x47d24705,
0x4be24bf3,0x416c3f40,0x4a7e4abf,0x48ad484d,0x4bae4bcb,0x447b4334,0x49eb4a37,0x49624909,0x4b604b8a,0x46314558,0x4946499b,0x4a0449b5,
0x4bfc4c00,0x3c060000,0x4ac14b02,0x484a47b7,0x4bdc4bf0,0x42014004,0x4a294a78,0x491b48b5,0x4b9c4bc0,0x44f343f7,0x497949d4,0x49d6497b,
0x4b3d4b70,0x46d245e5,0x48b24918,0x4a7a4a2b,0x4bfb4c00,0x3c6a0000,0x4a814ad0,0x48a84832,0x4bd44bed,0x42944067,0x49cd4a2b,0x49824918,
0x4b874bb2,0x456a445d,0x48fd4969,0x4a4149e5,0x4b164b53,0x476f4670,0x4815488c,0x4ae14a95,0x4bfa4c00,0x3cce0000,0x4a3d4a99,0x49024887,
0x4bcc4be9,0x432840cb,0x496b49d8,0x49e34976,0x4b714ba4,0x45df44bd,0x487a48f6,0x4aa24a47,0x4aeb4b33,0x480546f9,0x46dd47ee,0x4b3a4af3,
0x4bf94c00,0x3d330000,0x49f44a5e,0x495848d8,0x4bc34be5,0x43ba412e,0x49024980,0x4a3d49d0,0x4b594b95,0x4654451d,0x47dd487c,0x4af74aa0,
0x4abd4b11,0x48504780,0x458146b5,0x4b834b43,0x4bf84c00,0x3d970000,0x49a64a1f,0x49aa4927,0x4bba4be1,0x44264191,0x48944922,0x4a904a23,
0x4b3f4b84,0x46c6457c,0x46bb47f9,0x4b424af0,0x4a8c4aed,0x48994802,0x441a4570,0x4bbc4b86,0x4bf74c00,0x3dfb0000,0x495449dc,0x49f84972,
0x4bb04bdc,0x446f41f4,0x482048bf,0x4adb4a71,0x4b244b72,0x473745da,0x458d46ee,0x4b814b36,0x4a584ac6,0x48e04842,0x41534420,0x4be34bbb,
0x4bf64c00,0x3e5f0000,0x48fd4996,0x4a4149ba,0x4ba54bd7,0x44b74257,0x474e4858,0x4b1e4ab8,0x4b074b5f,0x47a64637,0x445745da,0x4bb34b72,
0x4a214a9c,0x49244881,0x3cce4191,0x4bfa4be1,0x4bf54c00,0x3ec30000,0x48a3494d,0x4a8549fe,0x4b9a4bd2,0x44ff42b9,0x465447d8,0x4b594af9,
0x4ae84b4b,0x480a4693,0x423244bd,0x4bd94ba4,0x49e74a71,0x496648bf,0xb4523db0,0x4c004bf8,0x4bf34c00,0x3f270000,0x48454900,0x4ac44a3f,
0x4b8e4bcd,0x4546431b,0x455246f9,0x4b8b4b33,0x4ac74b36,0x484046ee,0x3f594334,0x4bf24bcb,0x49aa4a43,0x49a648fb,0xbef52a48,0x4bf44c00,
0x4bf24c00,0x3f8b0000,0x47c848b0,0x4afe4a7c,0x4b814bc7,0x458d437d,0x444b4614,0x4bb54b67,0x4aa54b20,0x48744748,0x388440e4,0x4bff4be8,
0x496b4a13,0x49e34935,0xc263bd4c,0x4bd74bf9,0x4bf04c00,0x3fef0000,0x46ff485d,0x4b324ab5,0x4b734bc1,0x45d443df,0x427c4529,0x4bd64b93,
0x4a814b08,0x48a847a1,0xb9b13d1a,0x4bfe4bf9,0x492949e1,0x4a1d496d,0xc49fc160,0x4ba94be3,0x4bef4c00,0x40290000,0x46314807,0x4b604ae9,
0x4b654bbb,0x461a4420,0x405b4438,0x4bed4bb7,0x4a5c4af0,0x48db47f9,0xbfef2e48,0x4bf04c00,0x48e549ad,0x4a5449a4,0xc602c408,0x4b6a4bbe,
0x4bed4c00,0x405b0000,0x455e475e,0x4b894b1a,0x4b574bb4,0x465f4451,0x3c6a4288,0x4bfb4bd5,0x4a354ad6,0x490c4828,0xc27cbc51,0x4bd64bfb,
0x489e4976,0x4a8949d8,0xc759c558,0x4b1b4b8a,0x4beb4c00,0x408d0000,0x448746aa,0x4bac4b46,0x4b474bad,0x46a44481,0x26484099,0x4c004beb,
0x4a0d4abc,0x493c4852,0xc47bc080,0x4bae4bec,0x4855493e,0x4aba4a0b,0xc850c69e,0x4abd4b49,0x4be94c00,0x40be0000,0x435945f1,0x4bc94b6e,
0x4b374ba6,0x46e844b1,0xbc383d4c,0x4bfc4bf9,0x49e34aa0,0x496b487c,0xc5b1c2d2,0x4b7a4bd1,0x480a4905,0x4ae84a3b,0xc8eac7d8,0x4a504af9,
0x4be74c00,0x40f00000,0x419e4534,0x4be04b91,0x4b274b9e,0x472c44e1,0xc042357f,0x4bee4c00,0x49b84a83,0x499948a6,0xc6ddc48d,0x4b3a4bab,
0x477a48c9,0x4b134a69,0xc979c881,0x49d64a9c,0x4be54c00,0x41220000,0x3fbd4475,0x4bf14baf,0x4b164b97,0x476f4511,0xc263b91b,0x4bd74bfe,
0x498b4a65,0x49c548ce,0xc7fec5ab,0x4aee4b7b,0x46dd488c,0x4b3a4a95,0xc9fcc90e,0x494f4a33,0x4be34c00,0x41530000,0x3c384365,0x4bfc4bc9,
0x4b044b8f,0x47b24540,0xc43ebe78,0x4bb74bf6,0x495d4a47,0x49f048f6,0xc889c6c1,0x4a974b41,0x463c484d,0x4b5e4abf,0xca73c992,0x48bc49be,
0x4be14c00,0x41850000,0x317f41db,0x4c004bdd,0x4af14b86,0x47f34570,0xc546c12e,0x4b8e4be5,0x492e4a27,0x4a19491d,0xc90cc7cd,0x4a354afc,
0x4599480d,0x4b7f4ae6,0xcadbca0b,0x4820493e,0x4bdf4c00,0x41b60000,0xb9b1404e,0x4bfe4bed,0x4ade4b7d,0x481a459f,0xc648c31b,0x4b5c4bcd,
0x48fd4a07,0x4a414943,0xc986c867,0x49c94aae,0x44f34796,0x4b9c4b0b,0xcb35ca78,0x46f448b5,0x4bdd4c00,0x41e80000,0xbe5f3d7e,0x4bf64bf8,
0x4acb4b74,0x483a45ce,0xc742c481,0x4b214bad,0x48cc49e5,0x4a674969,0xc9f8c8e2,0x49544a56,0x444b4710,0x4bb54b2e,0xcb7fcad9,0x45994822,
0x4bda4c00,0x42190000,0xc0f038b6,0x4be74bff,0x4ab64b6b,0x485a45fd,0xc81ac570,0x4ade4b86,0x489949c3,0x4a8c498d,0xca60c956,0x48d649f6,
0x43404687,0x4bcb4b4e,0xcbb8cb2e,0x44324710,0x4bd84c00,0x424b0000,0xc2adb248,0x4bd34c00,0x4aa24b62,0x487a462b,0xc88ec659,0x4a934b58,
0x4865499f,0x4ab049b1,0xcabdc9c3,0x4850498d,0x41e845fd,0x4bdd4b6b,0xcbe1cb74,0x418545ce,0x4bd64c00,0x427c0000,0xc432bbd9,0x4bb84bfc,
0x4a8c4b58,0x48994659,0xc8fdc73d,0x4a414b22,0x4830497b,0x4ad149d4,0xcb10ca27,0x4785491d,0x408d4570,0x4beb4b86,0xcbf9cbad,0x3d334481,
0x4bd34c00,0x42ad0000,0xc50bbf0e,0x4b984bf4,0x4a764b4e,0x48b74687,0xc966c80d,0x49e74ae6,0x47f34956,0x4af149f6,0xcb57ca83,0x465f48a6,
0x3e5f44e1,0x4bf64b9e,0xcc00cbd7,0xb17f4257,0x4bd04c00,0x42de0000,0xc5dfc115,0x4b714be6,0x4a604b43,0x48d646b5,0xc9c9c877,0x49864aa3,
0x47854930,0x4b104a17,0xcb92cad6,0x452f4828,0x3b434451,0x4bfd4bb4,0xcbf5cbf3,0xbe913f40,0x4bce4c00,0x430f0000,0xc6afc2a1,0x4b454bd4,
0x4a494b39,0x48f346e3,0xca25c8dd,0x491f4a5a,0x47154909,0x4b2c4a37,0xcbc0cb20,0x43eb4748,0x3311437d,0x4c004bc7,0xcbd9cbff,0xc2323711,
0x4bcb4c00,0x43400000,0xc77ac414,0x4b134bbc,0x4a314b2e,0x49114710,0xca7ac93e,0x48b24a0b,0x46a448e2,0x4b474a56,0xcbe2cb5f,0x416c4637,
0xb7764257,0x4bff4bd7,0xcbaccbfd,0xc487bb75,0x4bc84c00,0x43710000,0xc820c4d5,0x4adb4ba0,0x4a194b22,0x492e473d,0xcac7c99b,0x484049b5,
0x463148ba,0x4b604a74,0xcbf8cb95,0x3dc9451d,0xbc9c412e,0x4bfb4be5,0xcb6fcbeb,0xc5ebc099,0x4bc54c00,0x43a20000,0xc87fc593,0x4a9e4b80,
0x4a004b17,0x494a476a,0xcb0dc9f2,0x4790495b,0x45bc4891,0x4b784a92,0xcc00cbc0,0x317f43f7,0xbf594004,0x4bf24bf0,0xcb21cbca,0xc742c34c,
0x4bc24c00,0x43d30000,0xc8dbc64e,0x4a5c4b5a,0x49e74b0b,0x49664796,0xcb4aca43,0x469948fb,0x45464867,0x4b8e4aae,0xcbfbcbe0,0xbc6a41aa,
0xc1093db0,0x4be64bf8,0xcac4cb9b,0xc845c4f9,0x4bbf4c00,0x44020000,0xc933c705,0x4a154b30,0x49cd4aff,0x498247c2,0xcb7fca8e,0x45994896,
0x44cf483d,0x4ba14ac9,0xcbe9cbf5,0xc0be3eaa,0xc2633aac,0x4bd74bfd,0xca58cb5d,0xc8e0c642,0x4bbc4c00,0x441a0000,0xc986c7b7,0x49c94b02,
0x49b34af3,0x499d47ee,0xcbabcad3,0x4493482d,0x44574812,0x4bb34ae3,0xcbcbcbff,0xc34037da,0xc3ba33db,0x4bc34c00,0xc9dfcb11,0xc970c780,
0x4bb84c00,0x44320000,0xc9d6c832,0x49794ad0,0x49994ae6,0x49b8480d,0xcbcecb11,0x430f4780,0x43ba47cd,0x4bc34afc,0xcb9fcbfe,0xc4dbb97f,
0xc487b57f,0x4bac4c00,0xc958cab8,0xc9f4c858,0x4bb54c00,0x444b0000,0xca21c887,0x49244a99,0x497d4ad9,0x49d24822,0xcbe7cb49,0x40f0469e,
0x42c64775,0x4bd24b14,0xcb68cbf2,0xc60ebf72,0xc52fbb75,0x4b924bfd,0xc8c7ca52,0xca6bc8e7,0x4bb24c00,0x44630000,0xca67c8d8,0x48cc4a5e,
0x49624acc,0x49eb4838,0xcbf8cb79,0x3d9745b6,0x41cf471b,0x4bde4b2b,0xcb24cbdb,0xc737c20d,0xc5d4be14,0x4b734bf7,0xc82ac9e1,0xcad5c96d,
0x4bae4c00,0x447b0000,0xcaa9c927,0x486f4a1f,0x49464abf,0x4a04484d,0xcc00cba2,0x351b44c9,0x40d746c1,0x4be84b41,0xcad5cbb9,0xc82ac42c,
0xc676c036,0x4b524bee,0xc70ac964,0xcb2fc9e9,0x4bab4c00,0x44930000,0xcae5c972,0x480f49dc,0x49294ab1,0x4a1d4862,0xcbfecbc4,0xba1643ae,
0x3fbd4665,0x4bf14b55,0xca7acb8c,0xc8b2c54c,0xc715c160,0x4b2c4be3,0xc5b1c8dd,0xcb7aca5a,0x4ba74c00,0x44ab0000,0xcb1bc9ba,0x47594996,
0x490c4aa3,0x4a354877,0xcbf2cbdf,0xbf5941c3,0x3dc94608,0x4bf84b69,0xca15cb55,0xc933c665,0xc7b2c288,0x4b044bd5,0xc44bc84d,0xcbb5cabf,
0x4ba34c00,0x44c30000,0xcb4cc9fe,0x468d494d,0x48ee4a95,0x4a4d488c,0xcbdecbf1,0xc1cf3fa4,0x3ba745ab,0x4bfc4b7b,0xc9a6cb14,0xc9aac775,
0xc825c3ae,0x4ad84bc4,0xc1b6c76a,0xcbdfcb17,0x4b9f4c00,0x44db0000,0xcb78ca3f,0x45bc4900,0x48d14a87,0x4a6448a0,0xcbc0cbfd,0xc3eb3b75,
0x3776454c,0x4bff4b8c,0xc92ecac9,0xca19c83d,0xc86fc469,0x4aa94bb1,0xbd97c62b,0xcbf8cb62,0x4b9c4c00,0x44f30000,0xcb9eca7c,0x44e748b0,
0x48b24a78,0x4a7a48b5,0xcb9acc00,0xc4ffaa48,0xa64844ed,0x4c004b9d,0xc8adca74,0xca7ec8ba,0xc8b7c4f9,0x4a764b9b,0x2cb6c4e1,0xcc00cb9e,
0x4b984c00,0x450b0000,0xcbbdcab5,0x440e485d,0x48944a69,0x4a9048c9,0xcb6acbfc,0xc602bc1f,0xb81f448d,0x4bff4bab,0xc825ca17,0xcad8c930,
0xc8fdc587,0x4a414b82,0x3e2dc31b,0xcbf6cbcd,0x4b944c00,0x45230000,0xcbd7cae9,0x42634807,0x48744a5a,0x4aa548dd,0xcb32cbf0,0xc6ffc004,
0xbc06442c,0x4bfc4bb9,0xc72cc9b1,0xcb27c99f,0xc941c614,0x4a094b67,0x4201c067,0xcbdccbed,0x4b904c00,0x453a0000,0xcbeacb1a,0x40a6475e,
0x48554a4b,0x4aba48f1,0xcaf1cbdc,0xc7f3c1f4,0xbdfb4396,0x4bf74bc6,0xc602c943,0xcb6aca07,0xc982c69e,0x49cd4b49,0x446fbaac,0xcbb0cbfd,
0x4b8b4c00,0x45520000,0xcbf8cb46,0x3dc946aa,0x48354a3b,0x4ace4905,0xcaa9cbc1,0xc86fc3df,0xbfef42d2,0x4bf04bd1,0xc4cfc8ce,0xcba1ca65,
0xc9c0c726,0x49904b28,0x45d43852,0xcb73cbff,0x4b874c00,0x456a0000,0xcbffcb6e,0x388445f1,0x48154a2b,0x4ae14918,0xca58cb9e,0xc8e0c4e1,
0xc0f0420d,0x4be74bdb,0xc328c852,0xcbcccabc,0xc9fcc7ac,0x494f4b05,0x472c3fa4,0xcb27cbf1,0x4b834c00,0x45810000,0xcc00cb91,0xb51b4534,
0x47e84a1b,0x4af4492b,0xca00cb74,0xc94ac5ce,0xc1e84147,0x4bdd4be4,0xc0a6c7a1,0xcbeacb08,0xca35c817,0x490c4ae0,0x483a4288,0xcacbcbd5,
0x4b7f4c00,0x45990000,0xcbfacbaf,0xbcce4475,0x47a64a0b,0x4b07493e,0xc9a1cb43,0xc9afc6b5,0xc2de4080,0x4bd04bec,0xbc38c693,0xcbfccb4b,
0xca6bc858,0x48c74ab8,0x48d64499,0xca60cbaa,0x4b7a4c00,0x45b10000,0xcbefcbc9,0xc0294365,0x476449fa,0x4b184951,0xc93ccb0b,0xca0dc796,
0xc3d33f72,0x4bc24bf2,0x3311c57c,0xcc00cb84,0xca9ec896,0x487f4a8e,0x496645e5,0xc9e7cb70,0x4b764c00,0x45c80000,0xcbddcbdd,0xc1e841db,
0x472149e9,0x4b2a4964,0xc8d1cacc,0xca64c838,0xc4633de2,0x4bb24bf7,0x3dfbc45d,0xcbf7cbb2,0xcacec8d3,0x48354a62,0x49eb4726,0xc962cb28,
0x4b714c00,0x45df0000,0xcbc5cbed,0xc3a2404e,0x46dd49d8,0x4b3a4976,0xc85fca87,0xcab3c8a0,0xc4db3c51,0x4b9f4bfb,0x4185c26f,0xcbe1cbd6,
0xcafbc90e,0x47d24a33,0x4a64482d,0xc8d1cad3,0x4b6c4c00,0x45f70000,0xcba7cbf8,0xc4ab3d7e,0x469949c7,0x4b4a4989,0xc7d2ca3b,0xcafbc905,
0xc552397f,0x4b8b4bfe,0x4402c01d,0xcbbfcbef,0xcb24c948,0x47374a02,0x4ace48bf,0xc835ca71,0x4b684c00,0x460e0000,0xcb83cbff,0xc58138b6,
0x465449b5,0x4b59499b,0xc6ddc9e9,0xcb3ac964,0xc5c834b6,0x4b764c00,0x453abb11,0xcb90cbfd,0xcb4ac980,0x469949d0,0x4b2a4948,0xc721ca02,
0x2c002c00,0x2c002c00,0x2c002c00,0x2c002c00,0x2b642c00,0x261f29a8,0xa61f0000,0xab64a9a8,0x29a82c00,0xa9a80000,0xa9a8ac00,0x29a80000,
0x261f2c00,0xab64a9a8,0x2b640000,0xa61f29a8,0x2c00,0xac00,0x2c00,0xac00,0xa61f2c00,0x2b64a9a8,0xab640000,0x261f29a8,
0xa9a82c00,0x29a80000,0x29a8ac00,0xa9a80000,0xab642c00,0xa61f29a8,0x261f0000,0x2b64a9a8,0,0,0,0,
0x261f0000,0x2b6429a8,0x2b642c00,0x261f29a8,0x29a80000,0x29a82c00,0xa9a80000,0xa9a8ac00,0x2b640000,0xa61f29a8,0xa61fac00,0x2b6429a8,
0x2c000000,0xac000000,0x2c000000,0xac000000,0x2b640000,0xa61fa9a8,0xa61f2c00,0x2b64a9a8,0x29a80000,0x29a8ac00,0xa9a80000,0xa9a82c00,
0x261f0000,0x2b64a9a8,0x2b64ac00,0x261fa9a8,0xac002c00,0xac002c00,0xac002c00,0xac002c00,0xab642c00,0xa61f29a8,0x261f0000,0x2b64a9a8,
0xa9a82c00,0x29a80000,0x29a8ac00,0xa9a80000,0xa61f2c00,0x2b64a9a8,0xab640000,0x261f29a8,0x2c00,0xac00,0x2c00,0xac00,
0x261f2c00,0xab64a9a8,0x2b640000,0xa61f29a8,0x29a82c00,0xa9a80000,0xa9a8ac00,0x29a80000,0x2b642c00,0x261f29a8,0xa61f0000,0xab64a9a8,
0,0,0,0,0xa61f0000,0xab6429a8,0xab642c00,0xa61f29a8,0xa9a80000,0xa9a82c00,0x29a80000,0x29a8ac00,
0xab640000,0x261f29a8,0x261fac00,0xab6429a8,0xac000000,0x2c000000,0xac000000,0x2c000000,0xab640000,0x261fa9a8,0x261f2c00,0xab64a9a8,
0xa9a80000,0xa9a8ac00,0x29a80000,0x29a82c00,0xa61f0000,0xab64a9a8,0xab64ac00,0xa61fa9a8,0,0,0,0,
0xa61f0000,0xab64a9a8,0xab64ac00,0xa61fa9a8,0xa9a80000,0xa9a8ac00,0x29a80000,0x29a82c00,0xab640000,0x261fa9a8,0x261f2c00,0xab64a9a8,
0xac000000,0x2c000000,0xac000000,0x2c000000,0xab640000,0x261f29a8,0x261fac00,0xab6429a8,0xa9a80000,0xa9a82c00,0x29a80000,0x29a8ac00,
0xa61f0000,0xab6429a8,0xab642c00,0xa61f29a8,0x2c002c00,0x2c002c00,0x2c002c00,0x2c002c00,0x2b642c00,0x261f29a8,0xa61f0000,0xab64a9a8,
0x29a82c00,0xa9a80000,0xa9a8ac00,0x29a80000,0x261f2c00,0xab64a9a8,0x2b640000,0xa61f29a8,0x2c00,0xac00,0x2c00,0xac00,
0xa61f2c00,0x2b64a9a8,0xab640000,0x261f29a8,0xa9a82c00,0x29a80000,0x29a8ac00,0xa9a80000,0xab642c00,0xa61f29a8,0x261f0000,0x2b64a9a8,
0,0,0,0,0x261f0000,0x2b64a9a8,0x2b64ac00,0x261fa9a8,0x29a80000,0x29a8ac00,0xa9a80000,0xa9a82c00,
0x2b640000,0xa61fa9a8,0xa61f2c00,0x2b64a9a8,0x2c000000,0xac000000,0x2c000000,0xac000000,0x2b640000,0xa61f29a8,0xa61fac00,0x2b6429a8,
0x29a80000,0x29a82c00,0xa9a80000,0xa9a8ac00,0x261f0000,0x2b6429a8,0x2b642c00,0x261f29a8,0xac002c00,0xac002c00,0xac002c00,0xac002c00,
0xab642c00,0xa61f29a8,0x261f0000,0x2b64a9a8,0xa9a82c00,0x29a80000,0x29a8ac00,0xa9a80000,0xa61f2c00,0x2b64a9a8,0xab640000,0x261f29a8,
0x2c00,0xac00,0x2c00,0xac00,0x261f2c00,0xab64a9a8,0x2b640000,0xa61f29a8,0x29a82c00,0xa9a80000,0xa9a8ac00,0x29a80000,
0x2b642c00,0x261f29a8,0xa61f0000,0xab64a9a8,0x2c002c00,0x2c002c00,0x2c002c00,0x2c002c00,0xab64ac00,0xa61fa9a8,0x261f0000,0x2b6429a8,
0x29a82c00,0xa9a80000,0xa9a8ac00,0x29a80000,0xa61fac00,0x2b6429a8,0xab640000,0x261fa9a8,0x2c00,0xac00,0x2c00,0xac00,
0x261fac00,0xab6429a8,0x2b640000,0xa61fa9a8,0xa9a82c00,0x29a80000,0x29a8ac00,0xa9a80000,0x2b64ac00,0x261fa9a8,0xa61f0000,0xab6429a8,
0,0,0,0,0xa61f0000,0xab64a9a8,0xab64ac00,0xa61fa9a8,0x29a80000,0x29a82c00,0xa9a80000,0xa9a8ac00,
0xab640000,0x261fa9a8,0x261f2c00,0xab64a9a8,0x2c000000,0xac000000,0x2c000000,0xac000000,0xab640000,0x261f29a8,0x261fac00,0xab6429a8,
0x29a80000,0x29a8ac00,0xa9a80000,0xa9a82c00,0xa61f0000,0xab6429a8,0xab642c00,0xa61f29a8,0xac002c00,0xac002c00,0xac002c00,0xac002c00,
0x2b64ac00,0x261fa9a8,0xa61f0000,0xab6429a8,0xa9a82c00,0x29a80000,0x29a8ac00,0xa9a80000,0x261fac00,0xab6429a8,0x2b640000,0xa61fa9a8,
0x2c00,0xac00,0x2c00,0xac00,0xa61fac00,0x2b6429a8,0xab640000,0x261fa9a8,0x29a82c00,0xa9a80000,0xa9a8ac00,0x29a80000,
0xab64ac00,0xa61fa9a8,0x261f0000,0x2b6429a8,0,0,0,0,0x261f0000,0x2b64a9a8,0x2b64ac00,0x261fa9a8,
0xa9a80000,0xa9a82c00,0x29a80000,0x29a8ac00,0x2b640000,0xa61fa9a8,0xa61f2c00,0x2b64a9a8,0xac000000,0x2c000000,0xac000000,0x2c000000,
0x2b640000,0xa61f29a8,0xa61fac00,0x2b6429a8,0xa9a80000,0xa9a8ac00,0x29a80000,0x29a82c00,0x261f0000,0x2b6429a8,0x2b642c00,0x261f29a8,
0,0,0,0,0x261f0000,0x2b6429a8,0x2b642c00,0x261f29a8,0xa9a80000,0xa9a8ac00,0x29a80000,0x29a82c00,
0x2b640000,0xa61f29a8,0xa61fac00,0x2b6429a8,0xac000000,0x2c000000,0xac000000,0x2c000000,0x2b640000,0xa61fa9a8,0xa61f2c00,0x2b64a9a8,
0xa9a80000,0xa9a82c00,0x29a80000,0x29a8ac00,0x261f0000,0x2b64a9a8,0x2b64ac00,0x261fa9a8,0x2c002c00,0x2c002c00,0x2c002c00,0x2c002c00,
0xab64ac00,0xa61fa9a8,0x261f0000,0x2b6429a8,0x29a82c00,0xa9a80000,0xa9a8ac00,0x29a80000,0xa61fac00,0x2b6429a8,0xab640000,0x261fa9a8,
0x2c00,0xac00,0x2c00,0xac00,0x261fac00,0xab6429a8,0x2b640000,0xa61fa9a8,0xa9a82c00,0x29a80000,0x29a8ac00,0xa9a80000,
0x2b64ac00,0x261fa9a8,0xa61f0000,0xab6429a8,0,0,0,0,0xa61f0000,0xab6429a8,0xab642c00,0xa61f29a8,
0x29a80000,0x29a8ac00,0xa9a80000,0xa9a82c00,0xab640000,0x261f29a8,0x261fac00,0xab6429a8,0x2c000000,0xac000000,0x2c000000,0xac000000,
0xab640000,0x261fa9a8,0x261f2c00,0xab64a9a8,0x29a80000,0x29a82c00,0xa9a80000,0xa9a8ac00,0xa61f0000,0xab64a9a8,0xab64ac00,0xa61fa9a8,
0xac002c00,0xac002c00,0xac002c00,0xac002c00,0x2b64ac00,0x261fa9a8,0xa61f0000,0xab6429a8,0xa9a82c00,0x29a80000,0x29a8ac00,0xa9a80000,
0x261fac00,0xab6429a8,0x2b640000,0xa61fa9a8,0x2c00,0xac00,0x2c00,0xac00,0xa61fac00,0x2b6429a8,0xab640000,0x261fa9a8,
0x29a82c00,0xa9a80000,0xa9a8ac00,0x29a80000,0xab64ac00,0xa61fa9a8,0x261f0000,0x2b6429a8,0x2bd92c00,0x2aa72b64,0x287229a8,0x223e261f,
0x2aa72c00,0xa23e261f,0xabd9a9a8,0xa872ab64,0x28722c00,0xabd9a61f,0x223ea9a8,0x2aa72b64,0x223e2c00,0xa872ab64,0x2aa729a8,0xabd9a61f,
0xa23e2c00,0x2872ab64,0xaaa729a8,0x2bd9a61f,0xa8722c00,0x2bd9a61f,0xa23ea9a8,0xaaa72b64,0xaaa72c00,0x223e261f,0x2bd9a9a8,0x2872ab64,
0xabd92c00,0xaaa72b64,0xa87229a8,0xa23e261f,0x223e0000,0x2872261f,0x2aa729a8,0x2bd92b64,0x28720000,0x2bd92b64,0x223e29a8,0xaaa7a61f,
0x2aa70000,0x223e2b64,0xabd9a9a8,0x2872a61f,0x2bd90000,0xaaa7261f,0x2872a9a8,0xa23e2b64,0x2bd90000,0xaaa7a61f,0x287229a8,0xa23eab64,
0x2aa70000,0x223eab64,0xabd929a8,0x2872261f,0x28720000,0x2bd9ab64,0x223ea9a8,0xaaa7261f,0x223e0000,0x2872a61f,0x2aa7a9a8,0x2bd9ab64,
0xabd92c00,0xaaa72b64,0xa87229a8,0xa23e261f,0xaaa72c00,0x223e261f,0x2bd9a9a8,0x2872ab64,0xa8722c00,0x2bd9a61f,0xa23ea9a8,0xaaa72b64,
0xa23e2c00,0x2872ab64,0xaaa729a8,0x2bd9a61f,0x223e2c00,0xa872ab64,0x2aa729a8,0xabd9a61f,0x28722c00,0xabd9a61f,0x223ea9a8,0x2aa72b64,
0x2aa72c00,0xa23e261f,0xabd9a9a8,0xa872ab64,0x2bd92c00,0x2aa72b64,0x287229a8,0x223e261f,0xa23e0000,0xa872261f,0xaaa729a8,0xabd92b64,
0xa8720000,0xabd92b64,0xa23e29a8,0x2aa7a61f,0xaaa70000,0xa23e2b64,0x2bd9a9a8,0xa872a61f,0xabd90000,0x2aa7261f,0xa872a9a8,0x223e2b64,
0xabd90000,0x2aa7a61f,0xa87229a8,0x223eab64,0xaaa70000,0xa23eab64,0x2bd929a8,0xa872261f,0xa8720000,0xabd9ab64,0xa23ea9a8,0x2aa7261f,
0xa23e0000,0xa872a61f,0xaaa7a9a8,0xabd9ab64,0xa23e0000,0xa872a61f,0xaaa7a9a8,0xabd9ab64,0xa8720000,0xabd9ab64,0xa23ea9a8,0x2aa7261f,
0xaaa70000,0xa23eab64,0x2bd929a8,0xa872261f,0xabd90000,0x2aa7a61f,0xa87229a8,0x223eab64,0xabd90000,0x2aa7261f,0xa872a9a8,0x223e2b64,
0xaaa70000,0xa23e2b64,0x2bd9a9a8,0xa872a61f,0xa8720000,0xabd92b64,0xa23e29a8,0x2aa7a61f,0xa23e0000,0xa872261f,0xaaa729a8,0xabd92b64,
0x2bd92c00,0x2aa72b64,0x287229a8,0x223e261f,0x2aa72c00,0xa23e261f,0xabd9a9a8,0xa872ab64,0x28722c00,0xabd9a61f,0x223ea9a8,0x2aa72b64,
0x223e2c00,0xa872ab64,0x2aa729a8,0xabd9a61f,0xa23e2c00,0x2872ab64,0xaaa729a8,0x2bd9a61f,0xa8722c00,0x2bd9a61f,0xa23ea9a8,0xaaa72b64,
0xaaa72c00,0x223e261f,0x2bd9a9a8,0x2872ab64,0xabd92c00,0xaaa72b64,0xa87229a8,0xa23e261f,0x223e0000,0x2872a61f,0x2aa7a9a8,0x2bd9ab64,
0x28720000,0x2bd9ab64,0x223ea9a8,0xaaa7261f,0x2aa70000,0x223eab64,0xabd929a8,0x2872261f,0x2bd90000,0xaaa7a61f,0x287229a8,0xa23eab64,
0x2bd90000,0xaaa7261f,0x2872a9a8,0xa23e2b64,0x2aa70000,0x223e2b64,0xabd9a9a8,0x2872a61f,0x28720000,0x2bd92b64,0x223e29a8,0xaaa7a61f,
0x223e0000,0x2872261f,0x2aa729a8,0x2bd92b64,0xabd92c00,0xaaa72b64,0xa87229a8,0xa23e261f,0xaaa72c00,0x223e261f,0x2bd9a9a8,0x2872ab64,
0xa8722c00,0x2bd9a61f,0xa23ea9a8,0xaaa72b64,0xa23e2c00,0x2872ab64,0xaaa729a8,0x2bd9a61f,0x223e2c00,0xa872ab64,0x2aa729a8,0xabd9a61f,
0x28722c00,0xabd9a61f,0x223ea9a8,0x2aa72b64,0x2aa72c00,0xa23e261f,0xabd9a9a8,0xa872ab64,0x2bd92c00,0x2aa72b64,0x287229a8,0x223e261f,
0xa23e0000,0xa872a61f,0xaaa7a9a8,0xabd9ab64,0x28720000,0x2bd92b64,0x223e29a8,0xaaa7a61f,0xaaa70000,0xa23eab64,0x2bd929a8,0xa872261f,
0x2bd90000,0xaaa7261f,0x2872a9a8,0xa23e2b64,0xabd90000,0x2aa7261f,0xa872a9a8,0x223e2b64,0x2aa70000,0x223eab64,0xabd929a8,0x2872261f,
0xa8720000,0xabd92b64,0xa23e29a8,0x2aa7a61f,0x223e0000,0x2872a61f,0x2aa7a9a8,0x2bd9ab64,0x2bd92c00,0x2aa72b64,0x287229a8,0x223e261f,
0xaaa7ac00,0x223ea61f,0x2bd929a8,0x28722b64,0x28722c00,0xabd9a61f,0x223ea9a8,0x2aa72b64,0xa23eac00,0x28722b64,0xaaa7a9a8,0x2bd9261f,
0xa23e2c00,0x2872ab64,0xaaa729a8,0x2bd9a61f,0x2872ac00,0xabd9261f,0x223e29a8,0x2aa7ab64,0xaaa72c00,0x223e261f,0x2bd9a9a8,0x2872ab64,
0x2bd9ac00,0x2aa7ab64,0x2872a9a8,0x223ea61f,0x223e0000,0x2872a61f,0x2aa7a9a8,0x2bd9ab64,0xa8720000,0xabd92b64,0xa23e29a8,0x2aa7a61f,
0x2aa70000,0x223eab64,0xabd929a8,0x2872261f,0xabd90000,0x2aa7261f,0xa872a9a8,0x223e2b64,0x2bd90000,0xaaa7261f,0x2872a9a8,0xa23e2b64,
0xaaa70000,0xa23eab64,0x2bd929a8,0xa872261f,0x28720000,0x2bd92b64,0x223e29a8,0xaaa7a61f,0xa23e0000,0xa872a61f,0xaaa7a9a8,0xabd9ab64,
0xabd92c00,0xaaa72b64,0xa87229a8,0xa23e261f,0x2aa7ac00,0xa23ea61f,0xabd929a8,0xa8722b64,0xa8722c00,0x2bd9a61f,0xa23ea9a8,0xaaa72b64,
0x223eac00,0xa8722b64,0x2aa7a9a8,0xabd9261f,0x223e2c00,0xa872ab64,0x2aa729a8,0xabd9a61f,0xa872ac00,0x2bd9261f,0xa23e29a8,0xaaa7ab64,
0x2aa72c00,0xa23e261f,0xabd9a9a8,0xa872ab64,0xabd9ac00,0xaaa7ab64,0xa872a9a8,0xa23ea61f,0xabd9ac00,0xaaa7ab64,0xa872a9a8,0xa23ea61f,
0x2aa72c00,0xa23e261f,0xabd9a9a8,0xa872ab64,0xa872ac00,0x2bd9261f,0xa23e29a8,0xaaa7ab64,0x223e2c00,0xa872ab64,0x2aa729a8,0xabd9a61f,
0x223eac00,0xa8722b64,0x2aa7a9a8,0xabd9261f,0xa8722c00,0x2bd9a61f,0xa23ea9a8,0xaaa72b64,0x2aa7ac00,0xa23ea61f,0xabd929a8,0xa8722b64,
0xabd92c00,0xaaa72b64,0xa87229a8,0xa23e261f,0xa23e0000,0xa872a61f,0xaaa7a9a8,0xabd9ab64,0x28720000,0x2bd92b64,0x223e29a8,0xaaa7a61f,
0xaaa70000,0xa23eab64,0x2bd929a8,0xa872261f,0x2bd90000,0xaaa7261f,0x2872a9a8,0xa23e2b64,0xabd90000,0x2aa7261f,0xa872a9a8,0x223e2b64,
0x2aa70000,0x223eab64,0xabd929a8,0x2872261f,0xa8720000,0xabd92b64,0xa23e29a8,0x2aa7a61f,0x223e0000,0x2872a61f,0x2aa7a9a8,0x2bd9ab64,
0x2bd9ac00,0x2aa7ab64,0x2872a9a8,0x223ea61f,0xaaa72c00,0x223e261f,0x2bd9a9a8,0x2872ab64,0x2872ac00,0xabd9261f,0x223e29a8,0x2aa7ab64,
0xa23e2c00,0x2872ab64,0xaaa729a8,0x2bd9a61f,0xa23eac00,0x28722b64,0xaaa7a9a8,0x2bd9261f,0x28722c00,0xabd9a61f,0x223ea9a8,0x2aa72b64,
0xaaa7ac00,0x223ea61f,0x2bd929a8,0x28722b64,0x2bd92c00,0x2aa72b64,0x287229a8,0x223e261f,0x223e0000,0x2872a61f,0x2aa7a9a8,0x2bd9ab64,
0xa8720000,0xabd92b64,0xa23e29a8,0x2aa7a61f,0x2aa70000,0x223eab64,0xabd929a8,0x2872261f,0xabd90000,0x2aa7261f,0xa872a9a8,0x223e2b64,
0x2bd90000,0xaaa7261f,0x2872a9a8,0xa23e2b64,0xaaa70000,0xa23eab64,0x2bd929a8,0xa872261f,0x28720000,0x2bd92b64,0x223e29a8,0xaaa7a61f,
0xa23e0000,0xa872a61f,0xaaa7a9a8,0xabd9ab64,0x27fe2800,0x96480000,0x273b2764,0xa2d7a21f,0x27ea27f6,0x9cb29a46,0x26dd270e,0xa41da38b,
0x27c327d9,0x9fc69e3e,0x266d26a7,0xa4c4a472,0x278827a8,0xa164a0a5,0x25ed262f,0xa55fa513,0x27c32800,0x9fc60000,0xa4c4a21f,0xa66da764,
0x25ed270e,0xa55fa38b,0xa73ba62f,0xa2d7a513,0x21642472,0xa788a6a7,0xa7fea7d9,0x16489e3e,0x9cb21a46,0xa7eaa7f6,0xa6dda7a8,0x241d20a5,
0x273b2800,0xa2d70000,0xa55fa764,0x25ed221f,0x1fc62513,0xa7c3a62f,0x1cb2a0a5,0x27ea27a8,0xa4c49e3e,0xa66da7d9,0x26dd2472,0x241d26a7,
0xa7fea70e,0x9648a38b,0x278827f6,0xa1641a46,0x266d2800,0xa4c40000,0x26dd221f,0x241d2764,0xa16420a5,0xa788a7a8,0x25ed27f6,0xa55f9a46,
0xa7fea6a7,0x1648a472,0xa2d71e3e,0xa73ba7d9,0x9fc6a62f,0x27c32513,0xa7eaa70e,0x1cb2a38b,0x255f2800,0xa5ed0000,0x21642764,0xa788a21f,
0xa66d9a46,0xa4c4a7f6,0xa7c3a38b,0x9fc6a70e,0xa41da7d9,0x26dd1e3e,0x9cb2a6a7,0x27ea2472,0x273b20a5,0x22d727a8,0x27fe2513,0x1648262f,
0x241d2800,0xa6dd0000,0xa7eaa21f,0x9cb2a764,0xa7fea38b,0x9648a70e,0x2164a513,0x2788262f,0x22d7a472,0x273b26a7,0x255f27d9,0xa5ed1e3e,
0x24c427f6,0xa66d1a46,0xa7c3a0a5,0x9fc6a7a8,0x21642800,0xa7880000,0x1648a764,0x27fe221f,0xa6dda62f,0x241da513,0x24c427a8,0xa66d20a5,
0x27ea1e3e,0x1cb227d9,0xa7c3a472,0x1fc6a6a7,0xa55f238b,0xa5eda70e,0x273b9a46,0x22d727f6,0x1cb22800,0xa7ea0000,0x27c3221f,0x9fc62764,
0xa2d7a7a8,0x273ba0a5,0xa7fe9a46,0x9648a7f6,0x255f26a7,0xa5ed2472,0x27889e3e,0x216427d9,0xa6dda513,0x241da62f,0xa66d238b,0xa4c4a70e,
0x96482800,0xa7fe0000,0xa2d72764,0xa73ba21f,0x1cb2a7f6,0x27ea1a46,0x241da70e,0x26dd238b,0x9fc627d9,0xa7c39e3e,0xa4c426a7,0xa66da472,
0x2164a7a8,0x278820a5,0x255fa62f,0x25ed2513,0x9fc62800,0xa7c30000,0xa66da21f,0x24c4a764,0x255fa70e,0x25ed238b,0x22d7262f,0xa73b2513,
0xa7882472,0xa164a6a7,0x1648a7d9,0x27fe9e3e,0x27ea9a46,0x9cb227f6,0xa41d27a8,0xa6dda0a5,0xa2d72800,0xa73b0000,0x25eda764,0x255f221f,
0x27c3a513,0x1fc6262f,0xa7ea20a5,0x1cb2a7a8,0xa66d9e3e,0x24c4a7d9,0x241d2472,0xa6dd26a7,0x1648270e,0xa7fe238b,0x2164a7f6,0x27889a46,
0xa4c42800,0xa66d0000,0x241d221f,0xa6dd2764,0x2788a0a5,0xa16427a8,0x255fa7f6,0x25ed1a46,0x1648a6a7,0x27fea472,0xa73b1e3e,0x22d7a7d9,
0xa7c3262f,0x9fc6a513,0x9cb2270e,0xa7ea238b,0xa5ed2800,0xa55f0000,0xa7882764,0xa164a21f,0x24c41a46,0xa66d27f6,0x1fc6238b,0xa7c3270e,
0x26dda7d9,0x241d1e3e,0x27eaa6a7,0x1cb22472,0xa2d7a0a5,0x273ba7a8,0x9648a513,0x27fea62f,0xa6dd2800,0xa41d0000,0x9cb2a21f,0x27eaa764,
0x1648238b,0xa7fe270e,0xa7882513,0x2164a62f,0x273ba472,0xa2d726a7,0xa5ed27d9,0xa55f1e3e,0x266da7f6,0x24c49a46,0x1fc620a5,0xa7c327a8,
0xa7882800,0xa1640000,0x27fea764,0x9648221f,0xa41d262f,0xa6dd2513,0x266da7a8,0x24c4a0a5,0x1cb21e3e,0xa7ea27d9,0x1fc6a472,0x27c3a6a7,
0x25eda38b,0xa55f270e,0xa2d71a46,0x273ba7f6,0xa7ea2800,0x9cb20000,0x9fc6221f,0xa7c32764,0xa73b27a8,0xa2d720a5,0x16481a46,0xa7fe27f6,
0xa5ed26a7,0xa55f2472,0x21649e3e,0xa78827d9,0xa41d2513,0xa6dd262f,0x24c4a38b,0xa66d270e,0xa7fe2800,0x16480000,0xa73b2764,0x22d7a21f,
0xa7ea27f6,0x1cb29a46,0xa6dd270e,0x241da38b,0xa7c327d9,0x1fc69e3e,0xa66d26a7,0x24c4a472,0xa78827a8,0x2164a0a5,0xa5ed262f,0x255fa513,
0xa7c32800,0x1fc60000,0x24c4a21f,0x266da764,0xa5ed270e,0x255fa38b,0x273ba62f,0x22d7a513,0xa1642472,0x2788a6a7,0x27fea7d9,0x96489e3e,
0x1cb21a46,0x27eaa7f6,0x26dda7a8,0xa41d20a5,0xa73b2800,0x22d70000,0x255fa764,0xa5ed221f,0x9fc62513,0x27c3a62f,0x9cb2a0a5,0xa7ea27a8,
0x24c49e3e,0x266da7d9,0xa6dd2472,0xa41d26a7,0x27fea70e,0x1648a38b,0xa78827f6,0x21641a46,0xa66d2800,0x24c40000,0xa6dd221f,0xa41d2764,
0x216420a5,0x2788a7a8,0xa5ed27f6,0x255f9a46,0x27fea6a7,0x9648a472,0x22d71e3e,0x273ba7d9,0x1fc6a62f,0xa7c32513,0x27eaa70e,0x9cb2a38b,
0xa55f2800,0x25ed0000,0xa1642764,0x2788a21f,0x266d9a46,0x24c4a7f6,0x27c3a38b,0x1fc6a70e,0x241da7d9,0xa6dd1e3e,0x1cb2a6a7,0xa7ea2472,
0xa73b20a5,0xa2d727a8,0xa7fe2513,0x9648262f,0xa41d2800,0x26dd0000,0x27eaa21f,0x1cb2a764,0x27fea38b,0x1648a70e,0xa164a513,0xa788262f,
0xa2d7a472,0xa73b26a7,0xa55f27d9,0x25ed1e3e,0xa4c427f6,0x266d1a46,0x27c3a0a5,0x1fc6a7a8,0xa1642800,0x27880000,0x9648a764,0xa7fe221f,
0x26dda62f,0xa41da513,0xa4c427a8,0x266d20a5,0xa7ea1e3e,0x9cb227d9,0x27c3a472,0x9fc6a6a7,0x255f238b,0x25eda70e,0xa73b9a46,0xa2d727f6,
0x9cb22800,0x27ea0000,0xa7c3221f,0x1fc62764,0x22d7a7a8,0xa73ba0a5,0x27fe9a46,0x1648a7f6,0xa55f26a7,0x25ed2472,0xa7889e3e,0xa16427d9,
0x26dda513,0xa41da62f,0x266d238b,0x24c4a70e,0x16482800,0x27fe0000,0x22d72764,0x273ba21f,0x9cb2a7f6,0xa7ea1a46,0xa41da70e,0xa6dd238b,
0x1fc627d9,0x27c39e3e,0x24c426a7,0x266da472,0xa164a7a8,0xa78820a5,0xa55fa62f,0xa5ed2513,0x1fc62800,0x27c30000,0x266da21f,0xa4c4a764,
0xa55fa70e,0xa5ed238b,0xa2d7262f,0x273b2513,0x27882472,0x2164a6a7,0x9648a7d9,0xa7fe9e3e,0xa7ea9a46,0x1cb227f6,0x241d27a8,0x26dda0a5,
0x22d72800,0x273b0000,0xa5eda764,0xa55f221f,0xa7c3a513,0x9fc6262f,0x27ea20a5,0x9cb2a7a8,0x266d9e3e,0xa4c4a7d9,0xa41d2472,0x26dd26a7,
0x9648270e,0x27fe238b,0xa164a7f6,0xa7889a46,0x24c42800,0x266d0000,0xa41d221f,0x26dd2764,0xa788a0a5,0x216427a8,0xa55fa7f6,0xa5ed1a46,
0x9648a6a7,0xa7fea472,0x273b1e3e,0xa2d7a7d9,0x27c3262f,0x1fc6a513,0x1cb2270e,0x27ea238b,0x25ed2800,0x255f0000,0x27882764,0x2164a21f,
0xa4c41a46,0x266d27f6,0x9fc6238b,0x27c3270e,0xa6dda7d9,0xa41d1e3e,0xa7eaa6a7,0x9cb22472,0x22d7a0a5,0xa73ba7a8,0x1648a513,0xa7fea62f,
0x26dd2800,0x241d0000,0x1cb2a21f,0xa7eaa764,0x9648238b,0x27fe270e,0x27882513,0xa164a62f,0xa73ba472,0x22d726a7,0x25ed27d9,0x255f1e3e,
0xa66da7f6,0xa4c49a46,0x9fc620a5,0x27c327a8,0x27882800,0x21640000,0xa7fea764,0x1648221f,0x241d262f,0x26dd2513,0xa66da7a8,0xa4c4a0a5,
0x9cb21e3e,0x27ea27d9,0x9fc6a472,0xa7c3a6a7,0xa5eda38b,0x255f270e,0x22d71a46,0xa73ba7f6,0x27ea2800,0x1cb20000,0x1fc6221f,0x27c32764,
0x273b27a8,0x22d720a5,0x96481a46,0x27fe27f6,0x25ed26a7,0x255f2472,0xa1649e3e,0x278827d9,0x241d2513,0x26dd262f,0xa4c4a38b,0x266d270e,
0x255f25a8,0xa5eda5a8,0x2164221f,0xa788a764,0x24c42513,0xa66da62f,0x1fc620a5,0xa7c3a7a8,0x241d2472,0xa6dda6a7,0x1cb21e3e,0xa7eaa7d9,
0x22d7238b,0xa73ba70e,0x16481a46,0xa7fea7f6,0xa41da5a8,0x26dd25a8,0x27ea2764,0x1cb2221f,0x9648a0a5,0x27fe27a8,0x278827f6,0xa1649a46,
0x22d71e3e,0x273b27d9,0x255f26a7,0xa5eda472,0x266d2513,0x24c4262f,0x1fc6238b,0xa7c3a70e,0x216425a8,0xa788a5a8,0x1648a21f,0x27fe2764,
0xa41d9a46,0xa6dda7f6,0x266d238b,0x24c4270e,0xa7eaa6a7,0x9cb2a472,0x27c327d9,0x9fc61e3e,0xa5eda7a8,0x255f20a5,0x22d7262f,0xa73ba513,
0x9cb2a5a8,0x27ea25a8,0xa7c3a764,0x1fc6a21f,0x273b238b,0x22d7270e,0x9648a513,0x27fe262f,0x255f27d9,0xa5ed9e3e,0x27882472,0x216426a7,
0xa41d1a46,0xa6dda7f6,0x24c427a8,0xa66da0a5,0x964825a8,0xa7fea5a8,0xa2d7221f,0xa73ba764,0xa7eaa62f,0x1cb2a513,0xa6dda7a8,0x241da0a5,
0x1fc6a472,0x27c326a7,0x24c49e3e,0x266d27d9,0x2788270e,0xa164238b,0x25ed27f6,0xa55f1a46,0x1fc6a5a8,0x27c325a8,0x266d2764,0xa4c4221f,
0x25ed27a8,0xa55f20a5,0xa73b9a46,0xa2d7a7f6,0xa7889e3e,0xa164a7d9,0x1648a6a7,0x27fe2472,0x1cb2a62f,0x27ea2513,0x26dd270e,0xa41d238b,
0xa2d725a8,0xa73ba5a8,0x25eda21f,0x255f2764,0x9fc6a7f6,0x27c31a46,0x9cb2270e,0xa7eaa38b,0x266d26a7,0xa4c42472,0xa41da7d9,0x26dd9e3e,
0xa7fea0a5,0x9648a7a8,0x27882513,0xa164262f,0x24c4a5a8,0x266d25a8,0xa41da764,0x26dda21f,0xa164270e,0xa788a38b,0x25ed262f,0xa55f2513,
0x1648a7d9,0x27fe1e3e,0xa73ba472,0x22d7a6a7,0x1fc627f6,0xa7c31a46,0x27ea20a5,0x9cb227a8,0xa5ed25a8,0xa55fa5a8,0xa788221f,0xa164a764,
0x266da513,0x24c4262f,0x27c3a0a5,0x1fc627a8,0xa6dd2472,0xa41da6a7,0xa7ea1e3e,0x9cb2a7d9,0x273ba38b,0x22d7270e,0x27fe9a46,0x164827f6,
0x26dda5a8,0x241d25a8,0x1cb22764,0xa7ea221f,0xa7fe20a5,0x9648a7a8,0x2164a7f6,0x27881a46,0x273b1e3e,0xa2d727d9,0xa5ed26a7,0xa55fa472,
0xa4c4a513,0x266da62f,0x27c3a38b,0x1fc6270e,0xa78825a8,0xa164a5a8,0x27fea21f,0x96482764,0x26dd1a46,0xa41d27f6,0xa4c4a38b,0x266da70e,
0x9cb2a6a7,0x27eaa472,0x9fc627d9,0xa7c31e3e,0xa55f27a8,0xa5eda0a5,0x273ba62f,0x22d72513,0x27eaa5a8,0x1cb225a8,0x1fc6a764,0x27c3a21f,
0xa2d7a38b,0x273ba70e,0xa7fe2513,0x9648a62f,0xa5ed27d9,0xa55f9e3e,0x21642472,0xa78826a7,0x26dd9a46,0xa41d27f6,0x266da7a8,0x24c420a5,
0xa7fe25a8,0x1648a5a8,0xa73b221f,0x22d7a764,0x9cb2262f,0xa7ea2513,0xa41d27a8,0xa6dd20a5,0x27c3a472,0x9fc626a7,0x266d9e3e,0xa4c427d9,
0x2164a70e,0x2788a38b,0x255fa7f6,0x25ed9a46,0x27c3a5a8,0x9fc625a8,0xa4c42764,0xa66d221f,0x255fa7a8,0x25eda0a5,0x22d71a46,0xa73b27f6,
0xa1649e3e,0x2788a7d9,0x27fea6a7,0x96482472,0xa7ea262f,0x1cb2a513,0x241da70e,0x26dda38b,0xa73b25a8,0x22d7a5a8,0x255fa21f,0xa5ed2764,
0xa7c327f6,0x9fc69a46,0x27eaa70e,0x9cb2238b,0xa4c426a7,0xa66d2472,0x26dda7d9,0x241d9e3e,0x164820a5,0xa7fe27a8,0x2164a513,0x2788a62f,
0x266da5a8,0xa4c425a8,0x26dda764,0x241da21f,0x2788a70e,0xa164238b,0x255fa62f,0x25eda513,0x27fea7d9,0x96481e3e,0x22d7a472,0x273ba6a7,
0x27c3a7f6,0x1fc69a46,0x1cb2a0a5,0x27eaa7a8,0xa55f25a8,0x25eda5a8,0xa164221f,0x2788a764,0xa4c42513,0x266da62f,0x9fc620a5,0x27c3a7a8,
0xa41d2472,0x26dda6a7,0x9cb21e3e,0x27eaa7d9,0xa2d7238b,0x273ba70e,0x96481a46,0x27fea7f6,0x241da5a8,0xa6dd25a8,0xa7ea2764,0x9cb2221f,
0x1648a0a5,0xa7fe27a8,0xa78827f6,0x21649a46,0xa2d71e3e,0xa73b27d9,0xa55f26a7,0x25eda472,0xa66d2513,0xa4c4262f,0x9fc6238b,0x27c3a70e,
0xa16425a8,0x2788a5a8,0x9648a21f,0xa7fe2764,0x241d9a46,0x26dda7f6,0xa66d238b,0xa4c4270e,0x27eaa6a7,0x1cb2a472,0xa7c327d9,0x1fc61e3e,
0x25eda7a8,0xa55f20a5,0xa2d7262f,0x273ba513,0x1cb2a5a8,0xa7ea25a8,0x27c3a764,0x9fc6a21f,0xa73b238b,0xa2d7270e,0x1648a513,0xa7fe262f,
0xa55f27d9,0x25ed9e3e,0xa7882472,0xa16426a7,0x241d1a46,0x26dda7f6,0xa4c427a8,0x266da0a5,0x164825a8,0x27fea5a8,0x22d7221f,0x273ba764,
0x27eaa62f,0x9cb2a513,0x26dda7a8,0xa41da0a5,0x9fc6a472,0xa7c326a7,0xa4c49e3e,0xa66d27d9,0xa788270e,0x2164238b,0xa5ed27f6,0x255f1a46,
0x9fc6a5a8,0xa7c325a8,0xa66d2764,0x24c4221f,0xa5ed27a8,0x255f20a5,0x273b9a46,0x22d7a7f6,0x27889e3e,0x2164a7d9,0x9648a6a7,0xa7fe2472,
0x9cb2a62f,0xa7ea2513,0xa6dd270e,0x241d238b,0x22d725a8,0x273ba5a8,0xa5eda21f,0xa55f2764,0x1fc6a7f6,0xa7c31a46,0x1cb2270e,0x27eaa38b,
0xa66d26a7,0x24c42472,0x241da7d9,0xa6dd9e3e,0x27fea0a5,0x1648a7a8,0xa7882513,0x2164262f,0xa4c4a5a8,0xa66d25a8,0x241da764,0xa6dda21f,
0x2164270e,0x2788a38b,0xa5ed262f,0x255f2513,0x9648a7d9,0xa7fe1e3e,0x273ba472,0xa2d7a6a7,0x9fc627f6,0x27c31a46,0xa7ea20a5,0x1cb227a8,
0x25ed25a8,0x255fa5a8,0x2788221f,0x2164a764,0xa66da513,0xa4c4262f,0xa7c3a0a5,0x9fc627a8,0x26dd2472,0x241da6a7,0x27ea1e3e,0x1cb2a7d9,
0xa73ba38b,0xa2d7270e,0xa7fe9a46,0x964827f6,0xa6dda5a8,0xa41d25a8,0x9cb22764,0x27ea221f,0x27fe20a5,0x1648a7a8,0xa164a7f6,0xa7881a46,
0xa73b1e3e,0x22d727d9,0x25ed26a7,0x255fa472,0x24c4a513,0xa66da62f,0xa7c3a38b,0x9fc6270e,0x278825a8,0x2164a5a8,0xa7fea21f,0x16482764,
0xa6dd1a46,0x241d27f6,0x24c4a38b,0xa66da70e,0x1cb2a6a7,0xa7eaa472,0x1fc627d9,0x27c31e3e,0x255f27a8,0x25eda0a5,0xa73ba62f,0xa2d72513,
0xa7eaa5a8,0x9cb225a8,0x9fc6a764,0xa7c3a21f,0x22d7a38b,0xa73ba70e,0x27fe2513,0x1648a62f,0x25ed27d9,0x255f9e3e,0xa1642472,0x278826a7,
0xa6dd9a46,0x241d27f6,0xa66da7a8,0xa4c420a5,0x27fe25a8,0x9648a5a8,0x273b221f,0xa2d7a764,0x1cb2262f,0x27ea2513,0x241d27a8,0x26dd20a5,
0xa7c3a472,0x1fc626a7,0xa66d9e3e,0x24c427d9,0xa164a70e,0xa788a38b,0xa55fa7f6,0xa5ed9a46,0xa7c3a5a8,0x1fc625a8,0x24c42764,0x266d221f,
0xa55fa7a8,0xa5eda0a5,0xa2d71a46,0x273b27f6,0x21649e3e,0xa788a7d9,0xa7fea6a7,0x16482472,0x27ea262f,0x9cb2a513,0xa41da70e,0xa6dda38b,
0x273b25a8,0xa2d7a5a8,0xa55fa21f,0x25ed2764,0x27c327f6,0x1fc69a46,0xa7eaa70e,0x1cb2238b,0x24c426a7,0x266d2472,0xa6dda7d9,0xa41d9e3e,
0x964820a5,0x27fe27a8,0xa164a513,0xa788a62f,0xa66da5a8,0x24c425a8,0xa6dda764,0xa41da21f,0xa788a70e,0x2164238b,0xa55fa62f,0xa5eda513,
0xa7fea7d9,0x16481e3e,0xa2d7a472,0xa73ba6a7,0xa7c3a7f6,0x9fc69a46,0x9cb2a0a5,0xa7eaa7a8,
};

#define PROF(slot) do {} while (0)
#define PROF3(slot) do {} while (0)
#define PROF2(slot) do {} while (0)

__device__ __forceinline__ uint32_t smem_u32(const void* p) { return (uint32_t)__cvta_generic_to_shared(p); }

__device__ __forceinline__ void mbar_init(uint32_t a, uint32_t c) {
  asm volatile("mbarrier.init.shared::cta.b64 [%0], %1;\n" ::"r"(a), "r"(c) : "memory");
}
__device__ __forceinline__ void mbar_expect_tx(uint32_t a, uint32_t bytes) {
  asm volatile("mbarrier.arrive.expect_tx.shared::cta.b64 _, [%0], %1;\n" ::"r"(a), "r"(bytes) : "memory");
}
__device__ __forceinline__ void mbar_arrive_cluster(uint32_t cluster_addr) {
  asm volatile("mbarrier.arrive.shared::cluster.b64 _, [%0];\n" ::"r"(cluster_addr) : "memory");
}
__device__ __forceinline__ void mbar_arrive_cluster_n(uint32_t cluster_addr, uint32_t n) {
  asm volatile("mbarrier.arrive.shared::cluster.b64 _, [%0], %1;\n" ::"r"(cluster_addr), "r"(n) : "memory");
}
__device__ __forceinline__ bool mbar_try(uint32_t a, uint32_t parity) {
  uint32_t ok;
  asm volatile("{\n.reg .pred p;\nmbarrier.try_wait.parity.shared::cta.b64 p, [%1], %2;\nselp.u32 %0, 1, 0, p;\n}\n"
               : "=r"(ok) : "r"(a), "r"(parity) : "memory");
  return ok;
}
__device__ __forceinline__ void mbar_wait(uint32_t a, uint32_t parity) {
  if (mbar_try(a, parity)) return;
#pragma unroll 1
  for (int n = 0; n < SPIN_LIMIT; n++)
    if (mbar_try(a, parity)) break;
}
__device__ __forceinline__ bool elect_one() {
  uint32_t p;
  asm volatile("{\n.reg .pred P;\nelect.sync _|P, 0xffffffff;\nselp.u32 %0, 1, 0, P;\n}\n" : "=r"(p));
  return p;
}
__device__ __forceinline__ uint32_t mapa(uint32_t a, uint32_t rank) {
  uint32_t r;
  asm volatile("mapa.shared::cluster.u32 %0, %1, %2;\n" : "=r"(r) : "r"(a), "r"(rank));
  return r;
}
__device__ __forceinline__ void nb_sync(int id, int n) { asm volatile("bar.sync %0, %1;\n" ::"r"(id), "r"(n) : "memory"); }
__device__ __forceinline__ void nb_arrive(int id, int n) { asm volatile("bar.arrive %0, %1;\n" ::"r"(id), "r"(n) : "memory"); }
__device__ __forceinline__ void cluster_sync_all() {
  asm volatile("barrier.cluster.arrive.relaxed.aligned;\nbarrier.cluster.wait.aligned;\n" ::: "memory");
}
__device__ __forceinline__ void fence_async_smem() { asm volatile("fence.proxy.async.shared::cta;\n" ::: "memory"); }
__device__ __forceinline__ void fence_async_all() { asm volatile("fence.proxy.async.global;\n" ::: "memory"); }

__device__ __forceinline__ void tma_load_3d(uint32_t dst, const CUtensorMap* tm, uint32_t bar, int c0, int c1, int c2) {
  asm volatile(
      "cp.async.bulk.tensor.3d.shared::cluster.global.mbarrier::complete_tx::bytes [%0], [%1, {%3, %4, %5}], [%2];\n"
      ::"r"(dst), "l"(tm), "r"(bar), "r"(c0), "r"(c1), "r"(c2) : "memory");
}
__device__ __forceinline__ void tma_load_4d(uint32_t dst, const CUtensorMap* tm, uint32_t bar, int c0, int c1, int c2, int c3) {
  asm volatile(
      "cp.async.bulk.tensor.4d.shared::cluster.global.mbarrier::complete_tx::bytes [%0], [%1, {%3, %4, %5, %6}], [%2];\n"
      ::"r"(dst), "l"(tm), "r"(bar), "r"(c0), "r"(c1), "r"(c2), "r"(c3) : "memory");
}
__device__ __forceinline__ void tma_load_3d_mc(uint32_t dst, const CUtensorMap* tm, uint32_t bar, int c0, int c1, int c2) {
  asm volatile(
      "cp.async.bulk.tensor.3d.shared::cluster.global.mbarrier::complete_tx::bytes.multicast::cluster [%0], [%1, {%3, %4, %5}], [%2], %6;\n"
      ::"r"(dst), "l"(tm), "r"(bar), "r"(c0), "r"(c1), "r"(c2), "h"((uint16_t)3) : "memory");
}
__device__ __forceinline__ void tma_load_5d(uint32_t dst, const CUtensorMap* tm, uint32_t bar, int c0, int c4) {
  asm volatile(
      "cp.async.bulk.tensor.5d.shared::cluster.global.mbarrier::complete_tx::bytes [%0], [%1, {%3, %5, %5, %5, %4}], [%2];\n"
      ::"r"(dst), "l"(tm), "r"(bar), "r"(c0), "r"(c4), "r"(0) : "memory");
}
__device__ __forceinline__ void bulk_load(uint32_t dst, const void* src, uint32_t bytes, uint32_t bar) {
  asm volatile("cp.async.bulk.shared::cluster.global.mbarrier::complete_tx::bytes [%0], [%1], %2, [%3];\n"
               ::"r"(dst), "l"(src), "r"(bytes), "r"(bar) : "memory");
}
__device__ __forceinline__ void bulk_commit() { asm volatile("cp.async.bulk.commit_group;\n" ::: "memory"); }
__device__ __forceinline__ void bulk_wait0() { asm volatile("cp.async.bulk.wait_group 0;\n" ::: "memory"); }
__device__ __forceinline__ void prefetch_tmap(const CUtensorMap* tm) {
  asm volatile("prefetch.tensormap [%0];\n" ::"l"(tm) : "memory");
}

__device__ __forceinline__ void wg_fence() { asm volatile("wgmma.fence.sync.aligned;\n" ::: "memory"); }
__device__ __forceinline__ void wg_commit() { asm volatile("wgmma.commit_group.sync.aligned;\n" ::: "memory"); }
template <int N> __device__ __forceinline__ void wg_wait() {
  asm volatile("wgmma.wait_group.sync.aligned %0;\n" ::"n"(N) : "memory");
}
__device__ __forceinline__ uint64_t mkdesc(uint32_t addr, uint32_t lbo, uint32_t sbo, uint32_t swz) {
  return (uint64_t)((addr & 0x3FFFF) >> 4) | ((uint64_t)(lbo >> 4) << 16) | ((uint64_t)(sbo >> 4) << 32) |
         ((uint64_t)swz << 62);
}

#define R4(d, o) "+f"(d[o + 0]), "+f"(d[o + 1]), "+f"(d[o + 2]), "+f"(d[o + 3])
#define R8(d, o) R4(d, o), R4(d, o + 4)
#define R16(d, o) R8(d, o), R8(d, o + 8)
#define R32(d, o) R16(d, o), R16(d, o + 16)
#define R64(d, o) R32(d, o), R32(d, o + 32)

__device__ __forceinline__ void wgmma_n192(float (&d)[96], uint64_t da, uint64_t db, uint32_t acc) {
  asm volatile(
      "{\n.reg .pred p;\nsetp.ne.u32 p, %98, 0;\n"
      "wgmma.mma_async.sync.aligned.m64n192k16.f32.bf16.bf16 "
      "{%0,%1,%2,%3,%4,%5,%6,%7,%8,%9,%10,%11,%12,%13,%14,%15,%16,%17,%18,%19,%20,%21,%22,%23,%24,%25,%26,%27,%28,%29,%30,%31,"
      "%32,%33,%34,%35,%36,%37,%38,%39,%40,%41,%42,%43,%44,%45,%46,%47,%48,%49,%50,%51,%52,%53,%54,%55,%56,%57,%58,%59,%60,%61,%62,%63,"
      "%64,%65,%66,%67,%68,%69,%70,%71,%72,%73,%74,%75,%76,%77,%78,%79,%80,%81,%82,%83,%84,%85,%86,%87,%88,%89,%90,%91,%92,%93,%94,%95}, "
      "%96, %97, p, 1, 1, 0, 1;\n}\n"
      : R64(d, 0), R32(d, 64)
      : "l"(da), "l"(db), "r"(acc));
}
__device__ __forceinline__ void wgmma_n128(float (&d)[64], uint64_t da, uint64_t db, uint32_t acc) {
  asm volatile(
      "{\n.reg .pred p;\nsetp.ne.u32 p, %66, 0;\n"
      "wgmma.mma_async.sync.aligned.m64n128k16.f32.bf16.bf16 "
      "{%0,%1,%2,%3,%4,%5,%6,%7,%8,%9,%10,%11,%12,%13,%14,%15,%16,%17,%18,%19,%20,%21,%22,%23,%24,%25,%26,%27,%28,%29,%30,%31,"
      "%32,%33,%34,%35,%36,%37,%38,%39,%40,%41,%42,%43,%44,%45,%46,%47,%48,%49,%50,%51,%52,%53,%54,%55,%56,%57,%58,%59,%60,%61,%62,%63}, "
      "%64, %65, p, 1, 1, 0, 1;\n}\n"
      : R64(d, 0)
      : "l"(da), "l"(db), "r"(acc));
}
template <int N> __device__ __forceinline__ void fence_regs(float (&d)[N]) {
#pragma unroll
  for (int i = 0; i < N; i++) asm volatile("" : "+f"(d[i])::"memory");
}

__device__ __forceinline__ void mma16816(float (&d)[4], uint32_t a0, uint32_t a1, uint32_t a2, uint32_t a3, uint32_t b0,
                                         uint32_t b1) {
  asm("mma.sync.aligned.m16n8k16.row.col.f32.bf16.bf16.f32 {%0,%1,%2,%3}, {%4,%5,%6,%7}, {%8,%9}, {%0,%1,%2,%3};\n"
      : "+f"(d[0]), "+f"(d[1]), "+f"(d[2]), "+f"(d[3])
      : "r"(a0), "r"(a1), "r"(a2), "r"(a3), "r"(b0), "r"(b1));
}
__device__ __forceinline__ void mma16816_z(float (&d)[4], uint32_t a0, uint32_t a1, uint32_t a2, uint32_t a3, uint32_t b0,
                                           uint32_t b1) {
  asm("mma.sync.aligned.m16n8k16.row.col.f32.bf16.bf16.f32 {%0,%1,%2,%3}, {%4,%5,%6,%7}, {%8,%9}, {%10,%10,%10,%10};\n"
      : "=f"(d[0]), "=f"(d[1]), "=f"(d[2]), "=f"(d[3])
      : "r"(a0), "r"(a1), "r"(a2), "r"(a3), "r"(b0), "r"(b1), "f"(0.f));
}
__device__ __forceinline__ void ldsm4t(uint32_t (&r)[4], uint32_t a) {
  asm volatile("ldmatrix.sync.aligned.m8n8.x4.trans.shared.b16 {%0,%1,%2,%3}, [%4];\n"
               : "=r"(r[0]), "=r"(r[1]), "=r"(r[2]), "=r"(r[3]) : "r"(a) : "memory");
}
__device__ __forceinline__ void ldsm2t(uint32_t& r0, uint32_t& r1, uint32_t a) {
  asm volatile("ldmatrix.sync.aligned.m8n8.x2.trans.shared.b16 {%0,%1}, [%2];\n" : "=r"(r0), "=r"(r1) : "r"(a) : "memory");
}
__device__ __forceinline__ void st_async128(uint32_t a, uint32_t bar, uint32_t x, uint32_t y, uint32_t z, uint32_t w) {
  asm volatile("st.async.weak.shared::cluster.mbarrier::complete_tx::bytes.v4.b32 [%0], {%2,%3,%4,%5}, [%1];\n"
               ::"r"(a), "r"(bar), "r"(x), "r"(y), "r"(z), "r"(w) : "memory");
}
__device__ __forceinline__ void mbar_arrive(uint32_t a) {
  asm volatile("mbarrier.arrive.shared::cta.b64 _, [%0];\n" ::"r"(a) : "memory");
}
__device__ __forceinline__ void stsm4(uint32_t a, uint32_t r0, uint32_t r1, uint32_t r2, uint32_t r3) {
  asm volatile("stmatrix.sync.aligned.m8n8.x4.shared.b16 [%0], {%1,%2,%3,%4};\n"
               ::"r"(a), "r"(r0), "r"(r1), "r"(r2), "r"(r3) : "memory");
}
__device__ __forceinline__ void stsm4t(uint32_t a, uint32_t r0, uint32_t r1, uint32_t r2, uint32_t r3) {
  asm volatile("stmatrix.sync.aligned.m8n8.x4.trans.shared.b16 [%0], {%1,%2,%3,%4};\n"
               ::"r"(a), "r"(r0), "r"(r1), "r"(r2), "r"(r3) : "memory");
}
__device__ __forceinline__ uint2 lds64(uint32_t a) {
  uint2 v;
  asm volatile("ld.shared.v2.u32 {%0,%1}, [%2];\n" : "=r"(v.x), "=r"(v.y) : "r"(a));
  return v;
}
__device__ __forceinline__ uint4 lds128(uint32_t a) {
  uint4 v;
  asm volatile("ld.shared.v4.u32 {%0,%1,%2,%3}, [%4];\n" : "=r"(v.x), "=r"(v.y), "=r"(v.z), "=r"(v.w) : "r"(a) : "memory");
  return v;
}
__device__ __forceinline__ void sts128(uint32_t a, uint32_t x, uint32_t y, uint32_t z, uint32_t w) {
  asm volatile("st.shared.v4.u32 [%0], {%1,%2,%3,%4};\n" ::"r"(a), "r"(x), "r"(y), "r"(z), "r"(w) : "memory");
}
__device__ __forceinline__ uint32_t pack_bf16(float lo, float hi) {
  uint32_t r;
  asm("cvt.rn.bf16x2.f32 %0, %1, %2;\n" : "=r"(r) : "f"(hi), "f"(lo));
  return r;
}
__device__ __forceinline__ uint32_t bmul2(uint32_t a, uint32_t b) {
  uint32_t r;
  asm("mul.rn.bf16x2 %0, %1, %2;\n" : "=r"(r) : "r"(a), "r"(b));
  return r;
}
__device__ __forceinline__ uint32_t bmax2(uint32_t a, uint32_t b) {
  uint32_t r;
  asm("max.bf16x2 %0, %1, %2;\n" : "=r"(r) : "r"(a), "r"(b));
  return r;
}
__device__ __forceinline__ uint32_t bfma2(uint32_t a, uint32_t b, uint32_t c) {
  uint32_t r;
  asm("fma.rn.bf16x2 %0, %1, %2, %3;\n" : "=r"(r) : "r"(a), "r"(b), "r"(c));
  return r;
}
__device__ __forceinline__ uint32_t badd2(uint32_t a, uint32_t b) {
  uint32_t r;
  asm("add.rn.bf16x2 %0, %1, %2;\n" : "=r"(r) : "r"(a), "r"(b));
  return r;
}
__device__ __forceinline__ void prefetch_l2(const void* p) { asm volatile("prefetch.global.L2 [%0];\n" ::"l"(p)); }
__device__ __forceinline__ void cp_async16n(uint32_t dst, const void* src) {
  asm volatile("cp.async.cg.shared.global [%0], [%1], 16;\n" ::"r"(dst), "l"(src) : "memory");
}
__device__ __forceinline__ void cp_async16(uint32_t dst, const void* src, uint32_t srcbytes) {
  asm volatile("cp.async.cg.shared.global.L2::256B [%0], [%1], 16, %2;\n" ::"r"(dst), "l"(src), "r"(srcbytes) : "memory");
}
__device__ __forceinline__ uint32_t ld_acquire(const uint32_t* p) {
  uint32_t v;
  asm volatile("ld.acquire.gpu.global.u32 %0, [%1];\n" : "=r"(v) : "l"(p) : "memory");
  return v;
}
__device__ __forceinline__ uint32_t ld_relaxed(const uint32_t* p) {
  uint32_t v;
  asm volatile("ld.relaxed.gpu.global.u32 %0, [%1];\n" : "=r"(v) : "l"(p) : "memory");
  return v;
}
__device__ __forceinline__ void st_release(uint32_t* p, uint32_t v) {
  asm volatile("st.release.gpu.global.u32 [%0], %1;\n" ::"l"(p), "r"(v) : "memory");
}
__device__ __forceinline__ void wait_flag(const uint32_t* p, uint32_t want) {
  int n = 0;
  while (ld_relaxed(p) != want && ++n < SPIN_LIMIT) __nanosleep(40);
  (void)ld_acquire(p);
}

struct Params {
  const __nv_bfloat16* x;
  const __nv_bfloat16* w;
  const __nv_bfloat16* q;
  const __nv_bfloat16* k;
  const __nv_bfloat16* v;
  const __nv_bfloat16* shift_k;
  const __nv_bfloat16* ssm_k;
  const __nv_bfloat16* ssm_D;
  const __nv_bfloat16* wo;
  __nv_bfloat16* out;
};

__device__ __forceinline__ uint32_t lds32(uint32_t a) {
  uint32_t v;
  asm volatile("ld.shared.u32 %0, [%1];\n" : "=r"(v) : "r"(a));
  return v;
}
#define W4(d, o) "=f"(d[o + 0]), "=f"(d[o + 1]), "=f"(d[o + 2]), "=f"(d[o + 3])
#define W8(d, o) W4(d, o), W4(d, o + 4)
#define W16(d, o) W8(d, o), W8(d, o + 8)
#define U4(c, d, o) c(d[o + 0]), c(d[o + 1]), c(d[o + 2]), c(d[o + 3])
#define U8(c, d, o) U4(c, d, o), U4(c, d, o + 4)
#define U16(c, d, o) U8(c, d, o), U8(c, d, o + 8)
#define U32(c, d, o) U16(c, d, o), U16(c, d, o + 16)
#define D32 "{%0,%1,%2,%3,%4,%5,%6,%7,%8,%9,%10,%11,%12,%13,%14,%15,%16,%17,%18,%19,%20,%21,%22,%23,%24,%25,%26,%27,%28,%29,%30,%31}"
#define D16 "{%0,%1,%2,%3,%4,%5,%6,%7,%8,%9,%10,%11,%12,%13,%14,%15}"
#define D8 "{%0,%1,%2,%3,%4,%5,%6,%7}"
template <int ACC> __device__ __forceinline__ void hmma_n128t(uint32_t (&d)[32], const uint32_t (&a)[4], uint64_t db) {
  if (ACC)
    asm volatile("wgmma.mma_async.sync.aligned.m64n128k16.f16.f16.f16 " D32 ", {%32,%33,%34,%35}, %36, 1, 1, 1, 1;\n"
                 : U32("+r", d, 0) : "r"(a[0]), "r"(a[1]), "r"(a[2]), "r"(a[3]), "l"(db));
  else
    asm volatile("wgmma.mma_async.sync.aligned.m64n128k16.f16.f16.f16 " D32 ", {%32,%33,%34,%35}, %36, 0, 1, 1, 1;\n"
                 : U32("=r", d, 0) : "r"(a[0]), "r"(a[1]), "r"(a[2]), "r"(a[3]), "l"(db));
}
template <int ACC, int TB> __device__ __forceinline__ void hmma_n32(uint32_t (&d)[8], const uint32_t (&a)[4], uint64_t db) {
  if (ACC)
    asm volatile("wgmma.mma_async.sync.aligned.m64n32k16.f16.f16.f16 " D8 ", {%8,%9,%10,%11}, %12, 1, 1, 1, %13;\n"
                 : U8("+r", d, 0) : "r"(a[0]), "r"(a[1]), "r"(a[2]), "r"(a[3]), "l"(db), "n"(TB));
  else
    asm volatile("wgmma.mma_async.sync.aligned.m64n32k16.f16.f16.f16 " D8 ", {%8,%9,%10,%11}, %12, 0, 1, 1, %13;\n"
                 : U8("=r", d, 0) : "r"(a[0]), "r"(a[1]), "r"(a[2]), "r"(a[3]), "l"(db), "n"(TB));
}
template <int ACC> __device__ __forceinline__ void fmma_n32t(float (&d)[16], const uint32_t (&a)[4], uint64_t db) {
  if (ACC)
    asm volatile("wgmma.mma_async.sync.aligned.m64n32k16.f32.f16.f16 " D16 ", {%16,%17,%18,%19}, %20, 1, 1, 1, 1;\n"
                 : R16(d, 0) : "r"(a[0]), "r"(a[1]), "r"(a[2]), "r"(a[3]), "l"(db));
  else
    asm volatile("wgmma.mma_async.sync.aligned.m64n32k16.f32.f16.f16 " D16 ", {%16,%17,%18,%19}, %20, 0, 1, 1, 1;\n"
                 : W16(d, 0) : "r"(a[0]), "r"(a[1]), "r"(a[2]), "r"(a[3]), "l"(db));
}
template <int N> __device__ __forceinline__ void fence_regs(uint32_t (&d)[N]) {
#pragma unroll
  for (int i = 0; i < N; i++) asm volatile("" : "+r"(d[i])::"memory");
}
__device__ __forceinline__ uint32_t hmul(uint32_t a, uint32_t b) { uint32_t r; asm("mul.rn.f16x2 %0, %1, %2;\n" : "=r"(r) : "r"(a), "r"(b)); return r; }
__device__ __forceinline__ uint32_t hadd(uint32_t a, uint32_t b) { uint32_t r; asm("add.rn.f16x2 %0, %1, %2;\n" : "=r"(r) : "r"(a), "r"(b)); return r; }
__device__ __forceinline__ uint32_t hsub(uint32_t a, uint32_t b) { uint32_t r; asm("sub.rn.f16x2 %0, %1, %2;\n" : "=r"(r) : "r"(a), "r"(b)); return r; }
__device__ __forceinline__ uint32_t hfma(uint32_t a, uint32_t b, uint32_t c) { uint32_t r; asm("fma.rn.f16x2 %0, %1, %2, %3;\n" : "=r"(r) : "r"(a), "r"(b), "r"(c)); return r; }
__device__ __forceinline__ uint32_t hfnma(uint32_t a, uint32_t b, uint32_t c) {
  uint32_t r;
  asm("{\n.reg .b32 t;\nneg.f16x2 t, %1;\nfma.rn.f16x2 %0, t, %2, %3;\n}\n" : "=r"(r) : "r"(a), "r"(b), "r"(c));
  return r;
}
__device__ __forceinline__ uint32_t hrefl(uint32_t p, uint32_t s) {
  uint32_t r;
  asm("{\n.reg .b32 t;\nneg.f16x2 t, %2;\nfma.rn.f16x2 %0, %1, %3, t;\n}\n" : "=r"(r) : "r"(p), "r"(s), "r"(0x40004000u));
  return r;
}
__device__ __forceinline__ void bfly(uint32_t xr, uint32_t xi, uint32_t tr, uint32_t ti, uint32_t yr, uint32_t yi, uint32_t ur,
                                     uint32_t ui, uint32_t& sr, uint32_t& si, uint32_t& dr, uint32_t& di) {
  const uint32_t pr = hfnma(xi, ti, hmul(xr, tr)), pi = hfma(xi, tr, hmul(xr, ti));
  sr = hfnma(yi, ui, hfma(yr, ur, pr));
  si = hfma(yi, ur, hfma(yr, ui, pi));
  dr = hrefl(pr, sr);
  di = hrefl(pi, si);
}
template <int BH> __device__ __forceinline__ void fft_e1(const uint32_t (&d)[32], const uint32_t (&tw)[16], uint32_t (&a2)[2][2][4]) {
#pragma unroll
  for (int be = 0; be < 2; be++)
#pragma unroll
    for (int s = 0; s < 2; s++) {
      const int o = 16 * s + 8 * be + 2 * BH, p = 2 * BH;
      bfly(d[o], d[o + 1], tw[p], tw[p + 1], d[o + 4], d[o + 5], tw[p + 4], tw[p + 5], a2[be][0][s], a2[be][0][2 + s],
           a2[be][1][s], a2[be][1][2 + s]);
    }
}
__device__ __forceinline__ uint32_t hfms(uint32_t a, uint32_t b, uint32_t c) {
  uint32_t r;
  asm("{\n.reg .b32 t;\nneg.f16x2 t, %3;\nfma.rn.f16x2 %0, %1, %2, t;\n}\n" : "=r"(r) : "r"(a), "r"(b), "r"(c));
  return r;
}
template <int C, int J> __device__ __forceinline__ void fft_e2(const uint32_t (&d0)[8], const uint32_t (&d1)[8], uint32_t (&a3)[2][4]) {
  const uint32_t ur = d0[2 * J], ui = d0[4 + 2 * J], hr = d0[2 * J + 1], hi = d0[5 + 2 * J];
  const uint32_t vr = d1[2 * J], vi = d1[4 + 2 * J], gr = d1[2 * J + 1], gi = d1[5 + 2 * J];
  const uint32_t pr = hfnma(ui, hi, hmul(ur, hr)), pi = hfma(ui, hr, hmul(ur, hi));
  a3[0][2 + C] = pr;
  a3[0][C] = pi;
  a3[1][2 + C] = hfnma(vi, hi, hfma(vr, hr, hfnma(ui, gi, hfms(ur, gr, pi))));
  a3[1][C] = hfma(vi, hr, hfma(vr, hi, hfma(ui, gr, hfma(ur, gi, pr))));
}
__device__ __forceinline__ void fft_e3(const uint32_t (&d)[2][8], const uint32_t (&tw)[16], uint32_t zaddr) {
#pragma unroll
  for (int rho = 0; rho < 2; rho++) {
    uint32_t zr[4], zi[4];
#pragma unroll
    for (int nb = 0; nb < 4; nb++) {
      const uint32_t xi = d[nb >> 1][2 * (nb & 1) + rho], xr = d[nb >> 1][4 + 2 * (nb & 1) + rho];
      const uint32_t tr = tw[8 + 4 * rho + 2 * (nb & 1)], ti = tw[9 + 4 * rho + 2 * (nb & 1)];
      zr[nb] = hfnma(xi, ti, hmul(xr, tr));
      zi[nb] = hfma(xi, tr, hmul(xr, ti));
    }
    stsm4(zaddr + rho * 1024, zr[0], zr[1], zr[2], zr[3]);
    stsm4(zaddr + rho * 1024 + 512, zi[0], zi[1], zi[2], zi[3]);
  }
}
__device__ __forceinline__ float bf_lo(uint32_t v) {
  uint32_t r;
  asm("prmt.b32 %0, %1, 0, 0x1044;\n" : "=r"(r) : "r"(v));
  return __uint_as_float(r);
}
__device__ __forceinline__ float bf_hi(uint32_t v) { return __uint_as_float(v & 0xffff0000u); }
__device__ __forceinline__ float ex2(float x) {
  float r;
  asm("ex2.approx.ftz.f32 %0, %1;\n" : "=f"(r) : "f"(x));
  return r;
}
__device__ __forceinline__ float rcp(float x) {
  float r;
  asm("rcp.approx.ftz.f32 %0, %1;\n" : "=f"(r) : "f"(x));
  return r;
}

__device__ __forceinline__ int g2_a(int s) { return ((0xA1054 >> (4 * s)) & 15) * 16384; }
__device__ __forceinline__ int g2_b(int s) { return ((0xCDB32 >> (4 * s)) & 15) * 16384; }
static_assert(OFF_U == 10 * 16384 && OFF_H == 12 * 16384 && OFF_OP == 4 * 16384, "units");
__device__ __forceinline__ int y_slot(int wg, int it) {
  static_assert(T_B2 == T_TW + 8192 && T_A1 == T_B2 + 4096, "y slots");
  return OFF_T + T_TW + ((it + 3) & 3) * 4096 + wg * 2048;
}

__device__ __forceinline__ void to_arr(uint32_t (&d)[4], uint4 v) { d[0] = v.x; d[1] = v.y; d[2] = v.z; d[3] = v.w; }

__device__ __forceinline__ void attn_stage(uint32_t sb, int blk, int lane, const float (&acc)[96], uint32_t (&k1)[2][4]) {
  const int lr = lane & 7, lm = lane >> 3;
  const uint32_t base = sb + OFF_VP + (blk * 16 + lr + 8 * (lm & 1)) * 128;
#pragma unroll
  for (int i = 0; i < 8; i++) k1[i >> 2][i & 3] = pack_bf16(acc[34 + 4 * i], acc[35 + 4 * i]);
  const uint32_t kh = sb + OFF_KH + blk * 2048 + lane * 16;
  sts128(kh, k1[0][0], k1[0][1], k1[0][2], k1[0][3]);
  sts128(kh + 512, k1[1][0], k1[1][1], k1[1][2], k1[1][3]);
#pragma unroll
  for (int j = 0; j < 8; j += 2)
    stsm4(base + (((j + (lm >> 1)) ^ lr) << 4), pack_bf16(acc[64 + 4 * j], acc[65 + 4 * j]),
          pack_bf16(acc[66 + 4 * j], acc[67 + 4 * j]), pack_bf16(acc[68 + 4 * j], acc[69 + 4 * j]),
          pack_bf16(acc[70 + 4 * j], acc[71 + 4 * j]));
}
__device__ __forceinline__ void attn_pack(const float (&acc)[96], uint32_t (&qa)[2][8], uint32_t (&k0)[2][4]) {
#pragma unroll
  for (int hd = 0; hd < 2; hd++) {
#pragma unroll
    for (int i = 0; i < 8; i++) {
      asm volatile("cvt.rn.bf16x2.f32 %0, %1, %2;\n" : "=r"(qa[hd][i]) : "f"(acc[16 * hd + 2 * i + 1]), "f"(acc[16 * hd + 2 * i]));
    }
#pragma unroll
    for (int i = 0; i < 4; i++) {
      asm volatile("cvt.rn.bf16x2.f32 %0, %1, %2;\n" : "=r"(k0[hd][i]) : "f"(acc[33 + 16 * hd + 4 * i]), "f"(acc[32 + 16 * hd + 4 * i]));
    }
  }
}
__device__ __forceinline__ void attn_own(const uint32_t (&k0)[2][4], const uint32_t (&k1)[2][4], bool le0, bool le1,
                                         const uint32_t (&qa)[2][8], float (&l)[2][4]) {
#pragma unroll
  for (int hd = 0; hd < 2; hd++) {
    float s0[4], s1[4];
    mma16816_z(s0, qa[hd][0], qa[hd][1], qa[hd][2], qa[hd][3], k0[hd][0], k0[hd][1]);
    mma16816_z(s1, qa[hd][0], qa[hd][1], qa[hd][2], qa[hd][3], k1[hd][0], k1[hd][1]);
    mma16816(s0, qa[hd][4], qa[hd][5], qa[hd][6], qa[hd][7], k0[hd][2], k0[hd][3]);
    mma16816(s1, qa[hd][4], qa[hd][5], qa[hd][6], qa[hd][7], k1[hd][2], k1[hd][3]);
    l[hd][0] = s0[0];
    l[hd][1] = s0[1];
    l[hd][2] = le0 ? s1[2] : s0[2];
    l[hd][3] = le1 ? s1[3] : s0[3];
  }
}
template <int N> __device__ __forceinline__ void quad_softmax(float (&x)[N][2], uint32_t (&pp)[N]) {
  const float c2 = 1.4426950408889634f;
  uint32_t q[N], mx[N / 2];
#pragma unroll
  for (int n = 0; n < N; n++) {
    const uint32_t r = pack_bf16(x[n][0], x[n][1]);
    q[n] = bfma2(r, 0x3e353e35u, bmul2(r, 0x379e379eu));
    x[n][0] = bf_lo(q[n]);
    x[n][1] = bf_hi(q[n]);
  }
#pragma unroll
  for (int n = 0; n < N / 2; n++)
    mx[n] = bmax2(__byte_perm(q[2 * n], q[2 * n + 1], 0x5410), __byte_perm(q[2 * n], q[2 * n + 1], 0x7632));
#pragma unroll
  for (int o = 1; o <= 2; o++)
#pragma unroll
    for (int n = 0; n < N / 2; n++) mx[n] = bmax2(mx[n], __shfl_xor_sync(0xffffffffu, mx[n], o));
  float m[N], t[N];
#pragma unroll
  for (int n = 0; n < N / 2; n++) {
    m[2 * n] = bf_lo(mx[n]);
    m[2 * n + 1] = bf_hi(mx[n]);
  }
#pragma unroll
  for (int n = 0; n < N; n++) {
    const float nm = -m[n] * c2;
    x[n][0] = ex2(fmaf(x[n][0], c2, nm));
    x[n][1] = ex2(fmaf(x[n][1], c2, nm));
    t[n] = x[n][0] + x[n][1];
  }
#pragma unroll
  for (int o = 1; o <= 2; o++)
#pragma unroll
    for (int n = 0; n < N; n++) t[n] += __shfl_xor_sync(0xffffffffu, t[n], o);
#pragma unroll
  for (int n = 0; n < N; n++) {
    const float inv = rcp(t[n]);
    pp[n] = pack_bf16(x[n][0] * inv, x[n][1] * inv);
  }
}
__device__ __forceinline__ void attn_pv(uint32_t dst, const uint32_t (&va)[4], const uint32_t (&vb)[4], uint32_t pp,
                                        uint32_t maskLE) {
  const uint32_t b0 = pp & ~maskLE, b1 = pp & maskLE;
  float oa[4], ob[4];
  mma16816_z(oa, va[0], va[1], va[2], va[3], b0, b1);
  mma16816_z(ob, vb[0], vb[1], vb[2], vb[3], b0, b1);
  stsm4t(dst, pack_bf16(oa[0], oa[1]), pack_bf16(oa[2], oa[3]), pack_bf16(ob[0], ob[1]), pack_bf16(ob[2], ob[3]));
}

template <int MODE>
__global__ void __cluster_dims__(2, 1, 1) __launch_bounds__(NTHREADS, 1)
fused_kernel(const Params p, const __grid_constant__ CUtensorMap tmX, const __grid_constant__ CUtensorMap tmW,
             const __grid_constant__ CUtensorMap tmWo,
             const __grid_constant__ CUtensorMap tmQ,
             const __grid_constant__ CUtensorMap tmXh, const __grid_constant__ CUtensorMap tmWh) {
  extern __shared__ __align__(1024) uint8_t smem[];
  const uint32_t sb = smem_u32(smem);
  const uint32_t bars = sb + OFF_BAR;
  const int tid = threadIdx.x, lane = tid & 31, warp = __shfl_sync(0xffffffffu, tid >> 5, 0);
  const int rank = blockIdx.x & 1;
  const bool halo_cta = blockIdx.x < 4;
  if (halo_cta && MODE != 0) return;
  int grp, mem;
  {
    const int t = (blockIdx.x >> 1) - 4, u = t - 32;
    const int q7 = (u * 37) >> 8;
    const bool lo = (unsigned)t < 32u, mid = (unsigned)u < 28u;
    grp = lo ? (t & 7) : (mid ? 1 + u - 7 * q7 : 0);
    mem = lo ? (t >> 3) : (mid ? 4 + q7 : (t < 0 ? t + 6 : t - 54));
  }
  const int rg = (grp >> 2) * 4 + (mem >> 1), hp = (grp & 3) * 4 + (mem & 1) * 2 + rank;
  const int rb2 = (grp >> 2) * 8 + mem, cb2 = (grp & 3) * 2 + rank;
  const int chb = grp * 16 + mem * 2 + rank;
  const int cta = rg * 16 + hp;
  const int par = rg >> 2, gidx = rg & 3;

  if (tid < 256 && !halo_cta && MODE != 2) {
    const int r = tid >> 3, c = tid & 7;
    const uint32_t so = r * 128 + ((c ^ (r & 7)) << 4);
    const __nv_bfloat16* wg0 = p.w + (size_t)r * (3 * DM) + hp * 64 + c * 8;
    const __nv_bfloat16* xg0 = p.x + (size_t)(2 * (gidx * 256 + r) + par) * DM + c * 8;
#pragma unroll
    for (int j = 0; j < 3; j++) cp_async16n(sb + OFF_1B + j * 4096 + so, wg0 + j * DM);
#pragma unroll
    for (int i = 0; i < 8; i++) cp_async16n(sb + i * 4096 + so, xg0 + (size_t)i * 64 * DM);
    asm volatile("cp.async.commit_group;\n" ::: "memory");
  }
  if (tid == 256) {
    prefetch_tmap(halo_cta ? &tmXh : &tmX);
#pragma unroll
    for (int i = 0; i < NS1B; i++) mbar_init(bars + 8 * (BAR_FULLB + i), 1);
#pragma unroll
    for (int i = 0; i < NS1A; i++) mbar_init(bars + 8 * (BAR_FULLA + i), 1);
    asm volatile("fence.mbarrier_init.release.cluster;\n" ::: "memory");
    if (!halo_cta && MODE != 2) {
      mbar_expect_tx(bars + 8 * (BAR_FULLB + 1), STG1B);
      tma_load_3d(sb + OFF_1B + 1 * STG1B, &tmW, bars + 8 * (BAR_FULLB + 1), hp * 64, 32, 0);
      mbar_expect_tx(bars + 8 * (BAR_FULLB + 2), STG1B);
      tma_load_3d(sb + OFF_1B + 2 * STG1B, &tmW, bars + 8 * (BAR_FULLB + 2), hp * 64, 64, 0);
    } else {
      prefetch_tmap(&tmWh);
    }
  } else if (tid == 288) {
#pragma unroll
    for (int i = 0; i < NS1A; i++) mbar_init(bars + 8 * (BAR_EMPTYA + i), 4);
#pragma unroll
    for (int i = 0; i < NS1B; i++) mbar_init(bars + 8 * (BAR_EMPTYB + i), 2);
    asm volatile("fence.mbarrier_init.release.cluster;\n" ::: "memory");
  } else if (tid == 320) {
#pragma unroll
    for (int i = 0; i < NS2; i++) {
      mbar_init(bars + 8 * (BAR_FULL2 + i), 1);
      mbar_init(bars + 8 * (BAR_EMPTY2 + i), 4);
    }
    mbar_init(bars + 8 * BAR_DEAD, 2);
    mbar_init(bars + 8 * (BAR_DEAD + 1), 2);
    mbar_init(bars + 8 * BAR_X, 2);
    mbar_init(bars + 8 * BAR_REL, 1);
    asm volatile("fence.mbarrier_init.release.cluster;\n" ::: "memory");
  } else if (tid == 352) {
    mbar_init(bars + 8 * BAR_T, 1);
    mbar_init(bars + 8 * BAR_UH, 3);
    mbar_init(bars + 8 * BAR_LFREE, 4);
    mbar_init(bars + 8 * BAR_LAND, 1);
    mbar_init(bars + 8 * BAR_U, 1);
    mbar_init(bars + 8 * BAR_Q, 1);
    mbar_init(bars + 8 * BAR_STG, 9);
    asm volatile("fence.mbarrier_init.release.cluster;\n" ::: "memory");
  }
  if (warp == 8) PROF2(23);
  cluster_sync_all();
  if (warp == 8) PROF2(24);

  if (warp >= 8) {
    const int hw = warp - 8;
    const int lr = lane & 7, lm = lane >> 3;
    auto g1_issue_a = [&](int j, int s) {
      const uint32_t fb = bars + 8 * (BAR_FULLA + s);
      mbar_expect_tx(fb, STG1A);
      tma_load_3d_mc(sb + s * STG1A + rank * 16384, &tmX, fb, j * 64, par, gidx * 256 + rank * 128);
    };
    auto g1_issue_b = [&](int kb, int s) {
      const uint32_t fb = bars + 8 * (BAR_FULLB + s);
      mbar_expect_tx(fb, STG1B);
      tma_load_3d(sb + OFF_1B + s * STG1B, &tmW, fb, hp * 64, kb * 32, 0);
    };
    asm volatile("setmaxnreg.dec.sync.aligned.u32 %0;\n" :: "n"(REG_HELP));

    if (halo_cta) {
      if (hw == 0) {
        int s = 0, ph = 1;
#pragma unroll 1
        for (int kb = 0; kb < 16; kb++) {
          mbar_wait(bars + 8 * (BAR_EMPTYB + s), ph);
          const uint32_t fb = bars + 8 * (BAR_FULLB + s), st = sb + s * STGH;
          if (elect_one()) {
            mbar_expect_tx(fb, STGH);
            tma_load_4d(st, &tmXh, fb, kb * 64, 248, 0, 0);
            tma_load_3d(st + 8192, &tmWh, fb, 0, kb * 64, 16 + blockIdx.x * 4);
            tma_load_3d(st + 8192 + 32768, &tmWh, fb, 0, kb * 64, 32 + blockIdx.x * 4);
          }
          if (++s == 3) { s = 0; ph ^= 1; }
        }
      }
      __syncwarp();
    } else if (hw == 0) {
      uint32_t epoch = 0;
      if (lane < (MODE == 2 ? NS2 : 2)) mbar_arrive_cluster_n(mapa(bars, rank) + 8 * (BAR_EMPTY2 + lane), 4);
      if (MODE != 2) {
      epoch = ld_relaxed(g_flag_o + 2 * cta) + 1;
      if (lane == 0) {
        mbar_expect_tx(bars + 8 * BAR_U, 32768);
        mbar_expect_tx(bars + 8 * BAR_LAND, 32768);
        mbar_expect_tx(bars + 8 * BAR_Q, 32768);
        mbar_expect_tx(bars + 8 * BAR_T, T_END);
      }
      {
        int sa = 1, pha = 1, sbb = 2, phb = 1;
#pragma unroll 1
        for (int kb = 2; kb < 32; kb++) {
          if (!(kb & 1)) {
            mbar_wait(bars + 8 * (BAR_EMPTYA + sa), pha);
            if (elect_one()) g1_issue_a(kb >> 1, sa);
            if (++sa == NS1A) { sa = 0; pha ^= 1; }
          }
          mbar_wait(bars + 8 * (BAR_EMPTYB + sbb), phb);
          if (kb > 2 && elect_one()) g1_issue_b(kb, sbb);
          __syncwarp();
          if (kb >= PF0 && kb < PF0 + 12)
            prefetch_l2((kb < PF0 + 8 ? p.q + (size_t)chb * 16384 + (kb - PF0) * 2048 : p.wo + (size_t)chb * 8192 + (kb - PF0 - 8) * 2048) + lane * 64);
          if (kb == 4) PROF2(27);
          if (kb == 1) PROF2(38);
          if (kb == 2) PROF2(39);
          if (++sbb == NS1B) { sbb = 0; phb ^= 1; }
        }
      }
      static_assert(32 % NS1B == 2 && (32 / NS1B) % 2 == 0 && OFF_Q == OFF_1B && 2 * STG1B == 6 * 4096, "slots / parity of these loads");
      const uint8_t* tab = reinterpret_cast<const uint8_t*>(g_tab);
      if (lane == 0) {
        prefetch_tmap(&tmWo);
        prefetch_tmap(&tmQ);
        bulk_load(sb + OFF_T + T_A1, tab + T_A1, T_END - T_A1, bars + 8 * BAR_T);
        mbar_wait(bars + 8 * (BAR_EMPTYB + 2), 1);
        tma_load_5d(sb + OFF_Q + 6 * 4096, &tmQ, bars + 8 * BAR_Q, (chb & ~1) * 8, rank * 32 + 24);
        tma_load_5d(sb + OFF_Q + 7 * 4096, &tmQ, bars + 8 * BAR_Q, (chb & ~1) * 8, rank * 32 + 28);
        if (gidx != 0) wait_flag(g_flag_h + (hp >> 2), epoch);
      }
      __syncwarp();
      {
        uint4 hk0 = make_uint4(0, 0, 0, 0), hk1 = hk0, hv0 = hk0, hv1 = hk0;
        if (gidx != 0) {
          const uint4* src = g_halo + cta * 128 + lane;
          hk0 = __ldcg(src); hk1 = __ldcg(src + 32); hv0 = __ldcg(src + 64); hv1 = __ldcg(src + 96);
        }
        if (lane == 0) {
          mbar_wait(bars + 8 * (BAR_EMPTYB + 3), 1);
          bulk_load(sb + OFF_T, tab, T_TW, bars + 8 * BAR_T);
        }
        __syncwarp();
        PROF2(18);
        sts128(sb + OFF_L0 + 1024 + lane * 16, hk0.x, hk0.y, hk0.z, hk0.w);
        sts128(sb + OFF_L0 + 1536 + lane * 16, hk1.x, hk1.y, hk1.z, hk1.w);
        stsm4(sb + OFF_L0 + lr * 128 + ((lm ^ lr) << 4), hv0.x, hv0.y, hv0.z, hv0.w);
        stsm4(sb + OFF_L0 + lr * 128 + (((4 + lm) ^ lr) << 4), hv1.x, hv1.y, hv1.z, hv1.w);
        __syncwarp();
        if (lane == 0) {
          mbar_arrive(bars + 8 * BAR_STG);
          mbar_wait(bars + 8 * (BAR_EMPTYB + 4), 1);
          bulk_load(sb + OFF_T + T_TW, tab + T_TW, T_A1 - T_TW, bars + 8 * BAR_T);
          mbar_wait(bars + 8 * BAR_EMPTYB, 0);
#pragma unroll 1
          for (int i = 0; i < 6; i++) tma_load_5d(sb + OFF_Q + i * 4096, &tmQ, bars + 8 * BAR_Q, (chb & ~1) * 8, rank * 32 + i * 4);
        }
        __syncwarp();
      }
      }
      if (MODE != 1) {
        auto korder = [&](int i) {
          const int j = i < 10 ? i - 2 : i - 8;
          return MODE == 2 ? i : i < 2 ? hp ^ 1 ^ i : (((hp & ~1) ^ (i < 10 ? 2 : 0)) + (j >> 1) * 4 + (j & 1)) & 15;
        };
        if (MODE == 0) {
          mbar_wait(bars + 8 * (BAR_EMPTY2 + 2), 0);
          if (elect_one()) {
            mbar_expect_tx(bars + 8 * BAR_FULL2, STG2);
            tma_load_3d(sb + g2_b(0), &tmWo, bars + 8 * BAR_FULL2, 0, korder(0) * 64, cb2 * 2);
            tma_load_3d(sb + g2_b(1), &tmWo, bars + 8 * (BAR_FULL2 + 1), 0, korder(1) * 64, cb2 * 2);
          }
        }
        PROF2(20);
        const __nv_bfloat16* osrc = g_o + (size_t)(rb2 >> 1) * 16 * 16384 + ((rb2 & 1) * 2 + rank) * 4096;
        const uint32_t* flag = g_flag_o + (rb2 >> 1) * 32 + korder(lane & 15) * 2 + (rb2 & 1);
        uint32_t ready = MODE == 0 ? 0u : ~0u;
        int s = MODE == 0 ? 2 : 0, ph = 0;
#pragma unroll 1
        for (int i = s; i < 16; i++) {
          const int kb = korder(i);
          const uint32_t fb = bars + 8 * (BAR_FULL2 + s);
          if (!((ready >> i) & 1)) {
            int n = 0;
            do {
              ready = __ballot_sync(0xffffffffu, ld_acquire(flag) == epoch);
            } while (!((ready >> i) & 1) && ++n < SPIN_LIMIT);
            fence_async_all();
          }
          if (i == 2) PROF(21);
          mbar_wait(bars + 8 * (BAR_EMPTY2 + s), ph);
          if (elect_one()) {
            mbar_expect_tx(fb, STG2);
            asm volatile(
                "cp.async.bulk.shared::cluster.global.mbarrier::complete_tx::bytes.multicast::cluster [%0], [%1], %2, [%3], %4;\n"
                ::"r"(sb + g2_a(s) + rank * 8192), "l"(osrc + kb * 16384), "r"(8192), "r"(fb), "h"((uint16_t)3) : "memory");
            if (MODE != 0 || i >= 4) tma_load_3d(sb + g2_b(s), &tmWo, fb, 0, kb * 64, cb2 * 2);
          }
          if (++s == NS2) { s = 0; ph ^= 1; }
          if (i == 3) PROF(37);
        }
      }
      __syncwarp();
    } else if (MODE != 2) {
      {
        const int g = lane >> 2, t = lane & 3;
        uint32_t w[2][4];
#pragma unroll
        for (int h = 0; h < 2; h++) {
          const uint2 x = __ldg(reinterpret_cast<const uint2*>(p.shift_k + ((chb & ~1) * 8 + h * 8 + g) * 4));
          w[h][0] = __byte_perm(x.x, x.x, 0x1010);
          w[h][1] = __byte_perm(x.x, x.x, 0x3232);
          w[h][2] = __byte_perm(x.y, x.y, 0x1010);
          w[h][3] = __byte_perm(x.y, x.y, 0x3232);
        }
        auto swz = [](int r) { return (((r & 29) | ((r ^ (r >> 2)) & 2)) << 5) | (r & 16); };
        const uint32_t kring = sb + OFF_H + (hw - 1) * 8192, vring = kring + 4096;
        const int s0 = rank * 32 + (hw - 1) * 11, s1 = hw == 3 ? rank * 32 + 32 : s0 + 11;
        const size_t goff = (size_t)(lane >> 1) * DM + (chb & ~1) * 8 + (lane & 1) * 8;
        const __nv_bfloat16* kg = p.k + goff;
        const __nv_bfloat16* vg = p.v + goff;
        const uint32_t d0 = swz(lane >> 1) ^ ((lane & 1) << 4), d1 = swz(16 + (lane >> 1)) ^ ((lane & 1) << 4);
        auto issue = [&](int st) {
          const uint32_t so = (st & 3) << 10;
          cp_async16(kring + so + d0, kg + (size_t)st * 32 * DM, 16);
          cp_async16(kring + so + d1, kg + (size_t)(st * 32 + 16) * DM, 16);
          cp_async16(vring + so + d0, vg + (size_t)st * 32 * DM, 16);
          cp_async16(vring + so + d1, vg + (size_t)(st * 32 + 16) * DM, 16);
        };
        const int xa = 8 * (lr >> 1) + 2 * lm + (lr & 1), xb = 8 * (lr >> 1) - 4 + 2 * (lm & 1) + (lr & 1);
        const uint32_t la = swz(xa), lb = swz(xb & 31);
        const int backb = xb < 0 ? 1 : 0;
        const uint32_t ud[2] = {mapa(sb + OFF_U + g * 4096 + t * 16, 0), mapa(sb + OFF_U + g * 4096 + t * 16, 1)};
        const uint32_t ub[2] = {mapa(bars + 8 * BAR_U, 0), mapa(bars + 8 * BAR_U, 1)};
        if (lane == 0) mbar_wait(bars + 8 * (BAR_FULLB + NS1B - 1), 0);
        __syncwarp();
        if (lane >= 24) cp_async16(kring + (((s0 - 1) & 3) << 10) + d1, s0 > 0 ? kg + (size_t)(s0 * 32 - 16) * DM : kg, s0 > 0 ? 16 : 0);
        issue(s0);
        asm volatile("cp.async.commit_group;\n" ::: "memory");
        issue(s0 + 1);
        asm volatile("cp.async.commit_group;\n" ::: "memory");
#pragma unroll 1
        for (int st = s0; st < s1; st++) {
          if (st + 2 < s1) issue(st + 2);
          if (hw == 1 && st - s0 < 8) prefetch_l2(p.ssm_k + (size_t)(chb * 8 + st - s0) * SEQ + lane * 64);
          if (hw == 2 && st == s0 + 4 && lane < 2) prefetch_l2(g_tab + (chb * 2 + lane) * 32);
          const uint32_t uo = (st ^ ((g ^ (st >> 2)) & 1)) * 64;
          asm volatile("cp.async.commit_group;\n" ::: "memory");
          asm volatile("cp.async.wait_group 2;\n" ::: "memory");
          __syncwarp();
#pragma unroll
          for (int h = 0; h < 2; h++) {
            uint32_t e[6], vv[4], e4[4];
            ldsm4t(e4, kring + ((st & 3) << 10) + (la ^ (h << 4)));
            ldsm2t(e[0], e[1], kring + (((st - backb) & 3) << 10) + (lb ^ (h << 4)));
            ldsm4t(vv, vring + ((st & 3) << 10) + (la ^ (h << 4)));
            e[2] = e4[0]; e[3] = e4[1]; e[4] = e4[2]; e[5] = e4[3];
            uint32_t o[5];
#pragma unroll
            for (int i = 0; i < 5; i++) o[i] = __byte_perm(e[i], e[i + 1], 0x5432);
#pragma unroll
            for (int i = 0; i < 4; i++) {
              uint32_t a = bmul2(o[i], w[h][3]);
              a = bfma2(e[i + 1], w[h][2], a);
              a = bfma2(o[i + 1], w[h][1], a);
              a = bfma2(e[i + 2], w[h][0], a);
              vv[i] = bmul2(a, vv[i]);
            }
            st_async128(ud[h] + uo, ub[h], vv[0], vv[1], vv[2], vv[3]);
          }
          __syncwarp();
        }
        PROF(16);
      }
      {
        const int rw = (lane >> 3) + (lane & 4), ck = lane & 3;
        const uint32_t so = rw * 64 + ck * 16, dof = rw * 128 + ((ck ^ rw) << 4);
        const uint8_t* hsrc = reinterpret_cast<const uint8_t*>(p.ssm_k + (size_t)chb * 8 * SEQ) + so;
        const float dv = lane < 8 ? __bfloat162float(p.ssm_D[chb * 8 + lane]) : 0.f;
        uint32_t x[32];
        auto load = [&](const uint8_t* src, int i) {
          asm volatile("ld.v4.u32 {%0,%1,%2,%3}, [%4];\n" : "=r"(x[4 * i]), "=r"(x[4 * i + 1]), "=r"(x[4 * i + 2]), "=r"(x[4 * i + 3])
                       : "l"(src + i * 512) : "memory");
        };
#pragma unroll
        for (int i = 0; i < 8; i++) load(hsrc + (hw - 1) * 4096, i);
        nb_sync(NB_HELP3, 96);
        mbar_wait(bars + 8 * BAR_U, 0);
        int eh = 0;
#pragma unroll 1
        for (int n = 2 * (hw - 1); n < 16; n += (n & 1) ? 5 : 1) {
          const int c = n >> 1;
          const uint8_t* nsrc = (n & 1) ? hsrc + (c < 5 ? c + 3 : c) * 4096
                                        : smem + OFF_U + c * 4096 + (so ^ (((c ^ (lane >> 2)) & 1) << 6));
          const uint32_t dst = sb + ((n & 1) ? OFF_U : OFF_H) + c * 4096 + dof;
          const float dc = __shfl_sync(0xffffffffu, dv, c);
          const float h0 = bf_lo(x[0]) + ((lane | (n & 1)) == 0 ? dc : 0.f), h1 = bf_hi(x[0]);
          x[0] = pack_bf16(h0, h1);
          uint32_t m[2] = {x[0], x[1]};
#pragma unroll
          for (int i = 2; i < 32; i++) asm("max.xorsign.abs.bf16x2 %0, %0, %1;\n" : "+r"(m[i & 1]) : "r"(x[i]));
          asm("max.xorsign.abs.bf16x2 %0, %0, %1;\n" : "+r"(m[0]) : "r"(m[1]));
          const uint32_t e = max(__reduce_max_sync(0xffffffffu, max((m[0] >> 7) & 255u, (m[0] >> 23) & 255u)), 5u);
          const uint32_t sc = (259u - e) * 0x00800080u;
#pragma unroll
          for (int i = 0; i < 8; i++) {
            uint32_t o[4];
#pragma unroll
            for (int j = 0; j < 4; j++) {
              const uint32_t v = bmul2(x[4 * i + j], sc);
              asm("cvt.rn.f16x2.f32 %0, %1, %2;\n" : "=r"(o[j]) : "f"(bf_hi(v)), "f"(i + j == 0 ? h0 * bf_hi(sc) : bf_lo(v)));
            }
            sts128((dst + (i & 3) * 1024) ^ ((i >> 2) << 6), o[0], o[1], o[2], o[3]);
            load(nsrc, i);
          }
          if (n & 1) {
            const int f = min(max((int)e + eh - 129, 0), 254);
            if (lane == 0) asm volatile("st.shared.u32 [%0], %1;\n" ::"r"(sb + OFF_SC + c * 4), "r"(f << 23) : "memory");
          }
          eh = e;
        }
        fence_async_smem();
        __syncwarp();
        if (lane == 0) mbar_arrive(bars + 8 * BAR_UH);
        PROF(32);
      }
      if (hw < 3) {
        const uint32_t rb = mapa(bars, lane & 1);
        const uint32_t epoch = ld_relaxed(g_flag_o + 2 * cta + hw - 1) + 1;
        const bool own = hw - 1 == (rb2 & 1);
        nb_sync(NB_OREADY + hw - 1, 160);
        if (lane < 2) {
          mbar_arrive_cluster(rb + 8 * (BAR_EMPTY2 + 2));
          mbar_arrive_cluster(rb + 8 * (BAR_EMPTY2 + 3));
        }
        if (lane == 0) {
          if (own) {
            mbar_arrive(bars + 8 * BAR_X);
            mbar_wait(bars + 8 * BAR_REL, 0);
          }
          asm volatile("cp.async.bulk.global.shared::cta.bulk_group [%0], [%1], %2;\n" ::"l"(g_o + (size_t)cta * 16384 + (hw - 1) * 8192),
                       "r"(sb + OFF_OP + (own ? 16384 : 0)), "r"(16384) : "memory");
          bulk_commit();
          bulk_wait0();
          if (own) mbar_expect_tx(bars + 8 * (BAR_FULL2 + 1), 16384);
          else mbar_arrive_cluster(mapa(bars, rank ^ 1) + 8 * BAR_X);
          st_release(g_flag_o + 2 * cta + hw - 1, epoch);
          if (!own) mbar_arrive(bars + 8 * BAR_REL);
        }
        __syncwarp();
        PROF(own ? 17 : 19);
      } else {
        mbar_wait(bars + 8 * BAR_REL, 0);
        if (MODE == 0) {
          mbar_wait(bars + 8 * BAR_X, 0);
          if (elect_one())
            asm volatile("cp.async.bulk.shared::cluster.shared::cta.mbarrier::complete_tx::bytes [%0], [%1], %2, [%3];\n"
                         ::"r"(mapa(sb + OFF_OP, rank ^ 1)), "r"(sb + OFF_OP + 16384), "r"(16384),
                         "r"(mapa(bars + 8 * BAR_FULL2, rank ^ 1)) : "memory");
        }
        if (MODE == 0) {
          mbar_wait(bars + 8 * BAR_DEAD, 0);
          if (elect_one()) {
            tma_load_3d(sb + g2_b(2), &tmWo, bars + 8 * (BAR_FULL2 + 2), 0, ((hp & ~1) ^ 2) * 64, cb2 * 2);
            tma_load_3d(sb + g2_b(3), &tmWo, bars + 8 * (BAR_FULL2 + 3), 0, ((hp & ~1) ^ 3) * 64, cb2 * 2);
          }
        }
        __syncwarp();
      }
      {
        const int c8 = (4 * (lr >> 1) + 2 * (lm & 1) + (lr & 1)) & 7;
        const bool own = (lr >> 2) == rank;
        const uint32_t ya = sb + (own ? y_slot(c8 & 1, c8 >> 1) : OFF_LAND + c8 * 2048);
        const uint32_t yx = ((lm >> 1) ^ lr) << 4;
        const int row = (lane >> 3) * 8 + ((lane >> 2) & 1);
        uint2* og = reinterpret_cast<uint2*>(p.out + (size_t)(rank * 1024 + row) * (2 * DM) + (chb & ~1) * 8 + (lane & 3) * 4);
        const uint32_t qa = sb + OFF_Q + lane * 8;
        mbar_wait(bars + 8 * BAR_Q, 0);
        mbar_wait(bars + 8 * BAR_LAND, 0);
        PROF(33);
        const uint32_t t0 = clock();
#pragma unroll 1
        for (int j = hw - 1; j < 16; j += 3) {
          uint32_t y[4][4];
          uint2 q[8];
          while ((uint32_t)clock() - t0 < j * PACE) __nanosleep(40);
          const uint32_t qj = qa + j * 2048;
#pragma unroll
          for (int i = 0; i < 4; i++) ldsm4t(y[i], ya + j * 128 + (yx ^ (i << 5)));
#pragma unroll
          for (int i = 0; i < 8; i++) q[i] = lds64(qj + i * 256);
#pragma unroll
          for (int i = 0; i < 8; i++)
            og[(size_t)(j * 64 + (i >> 2) * 32 + (i & 3) * 2) * (2 * DM / 4)] =
                make_uint2(bmul2(q[i].x, y[i >> 1][2 * (i & 1)]), bmul2(q[i].y, y[i >> 1][2 * (i & 1) + 1]));
        }
      }
      PROF(22);
    }
    cluster_sync_all();
  } else {
    asm volatile("setmaxnreg.inc.sync.aligned.u32 %0;\n" :: "n"(REG_MATH));
    if (warp == 0) PROF2(26);
    const int wg = warp >> 2;
    const int wtid = tid & 127;
    const bool signaller = (wtid == 0) || (wtid == 32);
    const uint32_t rbars = mapa(bars, wtid >> 5 & 1);

    if (halo_cta) {
      const uint32_t epoch = ld_relaxed(g_flag_h + blockIdx.x) + 1;
      float acc0[64], acc1[64];
      int s = 0, ph = 0;
#pragma unroll 1
      for (int kb = 0; kb < 16; kb++) {
        mbar_wait(bars + 8 * (BAR_FULLB + s), ph);
        const uint32_t st = sb + s * STGH;
        const uint64_t da = mkdesc(st, 16, 1024, 1);
        const uint64_t db = mkdesc(st + 8192 + wg * 32768, 8192, 1024, 1);
        wg_fence();
#pragma unroll
        for (int kk = 0; kk < 4; kk++) {
          wgmma_n128(acc0, da + 2 * kk, db + 128 * kk, kb + kk);
          wgmma_n128(acc1, da + 2 * kk, db + 1024 + 128 * kk, kb + kk);
        }
        wg_commit();
        wg_wait<0>();
        if (wtid == 0) mbar_arrive(bars + 8 * (BAR_EMPTYB + s));
        if (++s == 3) { s = 0; ph ^= 1; }
      }
      fence_regs(acc0);
      fence_regs(acc1);
      if ((warp & 3) != 3) {
#pragma unroll
        for (int hh = 0; hh < 2; hh++) {
          uint4* dst = g_halo + ((hh * 4 + (warp & 3) + 1) * 16 + blockIdx.x * 4) * 128 + wg * 64 + lane;
#pragma unroll
          for (int j = 0; j < 4; j++) {
            const int o = 16 * j + 2 * hh;
            dst[(j >> 1) * 128 + (j & 1) * 32] =
                make_uint4(pack_bf16(acc0[o], acc0[o + 1]), pack_bf16(acc0[o + 4], acc0[o + 5]),
                           pack_bf16(acc0[o + 8], acc0[o + 9]), pack_bf16(acc0[o + 12], acc0[o + 13]));
            dst[(2 + (j >> 1)) * 128 + (j & 1) * 32] =
                make_uint4(pack_bf16(acc1[o], acc1[o + 1]), pack_bf16(acc1[o + 4], acc1[o + 5]),
                           pack_bf16(acc1[o + 8], acc1[o + 9]), pack_bf16(acc1[o + 12], acc1[o + 13]));
          }
        }
      }
      nb_sync(NB_G1DONE, 256);
      if (tid == 0) st_release(g_flag_h + blockIdx.x, epoch);
      PROF(36);
      cluster_sync_all();
      return;
    }

    if (MODE != 2) {
    {
      float acc0[96], acc1[96];
      int sa = 0, pha = 0, sbb = 0, phb = 0;
      asm volatile("cp.async.wait_group 0;\n" ::: "memory");
      fence_async_smem();
      nb_sync(NB_FIRST, 256);
      if (tid == 0) {
        mbar_arrive(bars + 8 * BAR_FULLA);
        mbar_arrive(bars + 8 * BAR_FULLB);
      }
      PROF(0 + wg);
#pragma unroll 1
      for (int kb = 0; kb < 30; kb++) {
        if (!(kb & 1)) mbar_wait(bars + 8 * (BAR_FULLA + sa), pha);
        mbar_wait(bars + 8 * (BAR_FULLB + sbb), phb);
        if (kb == 0) PROF2(0 + wg);
        if (kb == 4 && wg == 0) PROF2(28);
        if (kb == 8 && wg == 0) PROF2(29);
        if (kb == 16 && wg == 0) PROF2(30);
        const uint64_t da = mkdesc(sb + sa * STG1A + wg * 16384 + (kb & 1) * 64, 16, 1024, 1);
        const uint64_t db = mkdesc(sb + OFF_1B + sbb * STG1B, 4096, 1024, 1);
        wg_fence();
        wgmma_n192(acc0, da, db, kb);
        wgmma_n192(acc1, da + 512, db, kb);
        wgmma_n192(acc0, da + 2, db + 128, 1);
        wgmma_n192(acc1, da + 514, db + 128, 1);
        wg_commit();
        wg_wait<1>();
        if (kb > 0) {
          if (wtid == 64) mbar_arrive(bars + 8 * (BAR_EMPTYB + (sbb == 0 ? NS1B - 1 : sbb - 1)));
          if (!(kb & 1) && signaller) mbar_arrive_cluster(rbars + 8 * (BAR_EMPTYA + (sa == 0 ? NS1A - 1 : sa - 1)));
        }
        if (++sbb == NS1B) { sbb = 0; phb ^= 1; }
        if ((kb & 1) && ++sa == NS1A) { sa = 0; pha ^= 1; }
      }
      const int blk0 = wg * 8 + (warp & 3);
      const int lr = lane & 7, lm = lane >> 3;
      const bool le0 = 2 * (lane & 3) <= (lane >> 2), le1 = 2 * (lane & 3) + 1 <= (lane >> 2);
      const uint32_t maskLE = (le0 ? 0x0000FFFFu : 0u) | (le1 ? 0xFFFF0000u : 0u);
      uint32_t k0[2][2][4], k1[2][2][4], qa[2][2][8];
      float l[2][2][4];
      {
        static_assert(15 % NS1A == 0 && 30 % NS1B == 0, "slots of the last k blocks");
        mbar_wait(bars + 8 * BAR_FULLA, 1);
        mbar_wait(bars + 8 * BAR_FULLB, 0);
        mbar_wait(bars + 8 * (BAR_FULLB + 1), 0);
        const uint64_t da = mkdesc(sb + wg * 16384, 16, 1024, 1);
        const uint64_t db = mkdesc(sb + OFF_1B, 4096, 1024, 1);
        wg_fence();
#pragma unroll
        for (int i = 0; i < 4; i++) wgmma_n192(acc0, da + 2 * i, db + (i >> 1) * (STG1B >> 4) + (i & 1) * 128, 1);
        wg_commit();
        wg_wait<1>();
        if (wtid == 64) mbar_arrive(bars + 8 * (BAR_EMPTYB + NS1B - 1));
#pragma unroll
        for (int i = 0; i < 2; i++) wgmma_n192(acc1, da + 512 + 2 * i, db + (i >> 1) * (STG1B >> 4) + (i & 1) * 128, 1);
        wg_commit();
        wg_wait<1>();
        fence_regs(acc0);
        attn_stage(sb, blk0, lane, acc0, k1[0]);
#pragma unroll
        for (int i = 2; i < 4; i++) wgmma_n192(acc1, da + 512 + 2 * i, db + (i >> 1) * (STG1B >> 4) + (i & 1) * 128, 1);
        wg_commit();
        attn_pack(acc0, qa[0], k0[0]);
        wg_wait<0>();
        fence_regs(acc1);
      }
      if (wtid == 64) mbar_arrive(bars + 8 * BAR_EMPTYB);
      PROF(2 + wg);
      attn_stage(sb, blk0 + 4, lane, acc1, k1[1]);
      __syncwarp();
      if (lane == 0) mbar_arrive(bars + 8 * BAR_STG);
      mbar_wait(bars + 8 * BAR_U, 0);
      attn_pack(acc1, qa[1], k0[1]);
      attn_own(k0[0], k1[0], le0, le1, qa[0], l[0]);
      attn_own(k0[1], k1[1], le0, le1, qa[1], l[1]);
      const uint32_t cho[2] = {(uint32_t)(((lm & 1) ^ lr) << 4), (uint32_t)(((2 + (lm & 1)) ^ lr) << 4)};
      const uint32_t obase = sb + OFF_OP + (wg == (rb2 & 1) ? 16384 : 0) + ((warp & 3) * 16 + lr) * 128;
      mbar_wait(bars + 8 * BAR_STG, 0);
      {
        uint32_t km[4][4], va[8][4], vb[8][4], pp[8];
        float x[8][2];
#pragma unroll
        for (int n = 0; n < 4; n++) {
          const int blk = blk0 + 4 * (n >> 1);
          to_arr(km[n], lds128(sb + (blk == 0 ? OFF_L0 + 1024 : OFF_KH + (blk - 1) * 2048) + (n & 1) * 512 + lane * 16));
        }
#pragma unroll
        for (int n = 0; n < 8; n++) {
          const int vr = (blk0 + 4 * ((n >> 1) & 1)) * 16 - 8 + 8 * (n >> 2) + 8 * (lm >> 1);
          const uint32_t vrow = sb + (vr < 0 ? OFF_L0 : OFF_VP + vr * 128) + lr * 128;
          ldsm4t(va[n], vrow + (cho[0] ^ ((n & 1) << 6)));
          ldsm4t(vb[n], vrow + (cho[1] ^ ((n & 1) << 6)));
        }
        const bool first = blk0 == 0 && gidx == 0;
#pragma unroll
        for (int n = 0; n < 4; n++) {
          const uint32_t(&q)[8] = qa[n >> 1][n & 1];
          float sm[4];
          mma16816_z(sm, q[0], q[1], q[2], q[3], km[n][0], km[n][1]);
          mma16816(sm, q[4], q[5], q[6], q[7], km[n][2], km[n][3]);
          if (n < 2 && first) sm[0] = sm[1] = -1e9f / 0.17677669529663687f;
          x[n][0] = le0 ? l[n >> 1][n & 1][0] : sm[0];
          x[n][1] = le1 ? l[n >> 1][n & 1][1] : sm[1];
          x[4 + n][0] = l[n >> 1][n & 1][2];
          x[4 + n][1] = l[n >> 1][n & 1][3];
        }
        quad_softmax<8>(x, pp);
#pragma unroll
        for (int n = 7; n >= 0; n--)
          attn_pv(obase + ((n >> 1) & 1) * 8192 + (n >> 2) * 1024 + (((4 * (n & 1) + lm) ^ lr) << 4), va[n], vb[n], pp[n],
                  maskLE);
      }
      fence_async_smem();
      nb_arrive(NB_OREADY + wg, 160);
    }

    {
      const int w = warp & 3;
      uint32_t a1[2][4], a4[8][4], tw[16], d1[32];
      float d4[16];
      const uint32_t tb = sb + OFF_T + wtid * 16;
      PROF(34 + wg);
      mbar_wait(bars + 8 * BAR_T, 0);
      mbar_wait(bars + 8 * BAR_UH, 0);
      to_arr(a1[0], lds128(tb + T_A1));
      to_arr(a1[1], lds128(tb + T_A1 + 2048));
      const uint64_t dx = mkdesc(sb + OFF_U + wg * 4096, OFF_H - OFF_U, 1024, 1);
      const uint64_t dz = mkdesc(sb + OFF_U + wg * 4096, 512, 128, 0);
      const uint64_t db2 = mkdesc(sb + OFF_T + T_B2, 128, 256, 0);
      wg_fence();
      hmma_n128t<0>(d1, a1[0], dx);
      hmma_n128t<1>(d1, a1[1], dx + 128);
      wg_commit();
      auto ldtw = [&](int i) {
        const uint4 v = lds128(tb + T_TW + i * 2048);
        tw[4 * i] = v.x; tw[4 * i + 1] = v.y; tw[4 * i + 2] = v.z; tw[4 * i + 3] = v.w;
      };
      ldtw(0);
      ldtw(1);
      const uint32_t za = sb + (w < 2 ? OFF_U : OFF_H) + wg * 4096 + (w & 1) * 2048 + lane * 16;
      const uint32_t yl = (wtid ^ (4 * rank + wg)) * 16;
      const uint32_t yown = mapa(sb, rank) + yl, yrem = mapa(sb + OFF_LAND + wg * 2048, rank ^ 1) + yl;
      const uint32_t yb[2] = {mapa(bars + 8 * BAR_LAND, 0), mapa(bars + 8 * BAR_LAND, 1)};
      wg_wait<0>();
      fence_regs(d1);
      nb_sync(NB_WG + wg, 128);
      auto s4 = [&](int it) {
        wg_fence();
#pragma unroll
        for (int ks = 0; ks < 8; ks++) {
          const uint64_t d = dz + (it & 1) * 512 + (ks & 3) * 64 + (ks >> 2) * ((OFF_H - OFF_U) >> 4);
          if (ks == 0) fmma_n32t<0>(d4, a4[ks], d);
          else fmma_n32t<1>(d4, a4[ks], d);
        }
        wg_commit();
      };
      auto e4 = [&](int it) {
        fence_regs(d4);
        const float sc = __uint_as_float(lds32(sb + OFF_SC + wg * 4 + it * 8));
        uint32_t r[8];
#pragma unroll
        for (int i = 0; i < 8; i++) r[i] = pack_bf16(d4[2 * i] * sc, d4[2 * i + 1] * sc);
        const uint32_t o = (yown + y_slot(wg, it)) ^ ((it >> 1) << 5), m = (yrem + it * 4096) ^ ((it >> 1) << 5);
        if (it == 0) mbar_wait(bars + 8 * BAR_LFREE, 0);
        if (it == 3) mbar_wait(bars + 8 * (BAR_DEAD + 1), 0);
        st_async128(rank ? m : o, yb[0], r[0], r[2], r[1], r[3]);
        st_async128(rank ? o : m, yb[1], r[4], r[6], r[5], r[7]);
      };
      uint32_t a2[2][2][2][4], a3[2][2][4], d2[2][2][8], d3[2][8];
      auto s2a = [&]() {
        wg_fence();
#pragma unroll
        for (int c = 0; c < 4; c++) hmma_n32<0, 0>(d2[c & 1][c >> 1], a2[0][c & 1][c >> 1], db2 + (c >> 1) * 128);
      };
      auto s2b = [&]() {
        wg_fence();
#pragma unroll
        for (int c = 0; c < 4; c++) {
          hmma_n32<1, 0>(d2[c & 1][c >> 1], a2[1][c & 1][c >> 1], db2 + (c >> 1) * 128 + 64);
          if (c & 1) wg_commit();
        }
      };
      auto s1 = [&](int it) {
        hmma_n128t<0>(d1, a1[0], dx + it * 512);
        hmma_n128t<1>(d1, a1[1], dx + it * 512 + 128);
        wg_commit();
      };
      auto done = [&](int it) {
        if (it == 0) {
          if (signaller) mbar_arrive_cluster(rbars + 8 * BAR_LFREE);
        } else if (it >= 2 && wtid == 64) {
          mbar_arrive(bars + 8 * (BAR_DEAD + it - 2));
        }
        if (w == 0) PROF3(40 + 4 * wg + it);
      };
      fft_e1<0>(d1, tw, a2[0]);
      s2a();
      fft_e1<1>(d1, tw, a2[1]);
      s2b();
      s1(1);
      ldtw(2);
      ldtw(3);
#pragma unroll
      for (int i = 0; i < 8; i++) to_arr(a4[i], lds128(tb + T_A4 + i * 2048));
#pragma unroll
      for (int it = 0; it < 4; it++) {
        if (it == 0 || it == 3) wg_wait<2>(); else wg_wait<3>();
        fence_regs(d2[0][0]);
        fence_regs(d2[1][0]);
        fft_e2<0, 0>(d2[0][0], d2[1][0], a3[0]);
        fft_e2<0, 1>(d2[0][0], d2[1][0], a3[1]);
        if (it == 0 || it == 3) wg_wait<1>(); else wg_wait<2>();
        fence_regs(d2[0][1]);
        fence_regs(d2[1][1]);
        fft_e2<1, 0>(d2[0][1], d2[1][1], a3[0]);
        fft_e2<1, 1>(d2[0][1], d2[1][1], a3[1]);
        wg_fence();
        hmma_n32<0, 0>(d3[0], a3[0][0], db2);
        hmma_n32<0, 0>(d3[1], a3[0][1], db2);
        hmma_n32<1, 0>(d3[0], a3[1][0], db2 + 64);
        hmma_n32<1, 0>(d3[1], a3[1][1], db2 + 64);
        wg_commit();
        wg_wait<1>();
        if (it > 0) e4(it - 1);
        if (it < 3) {
          fence_regs(d1);
          fft_e1<0>(d1, tw, a2[0]);
        }
        wg_wait<0>();
        fence_regs(d3[0]);
        fence_regs(d3[1]);
        if (it < 3) s2a();
        fft_e3(d3, tw, za + (it & 1) * 8192);
        if (it < 3) {
          fft_e1<1>(d1, tw, a2[1]);
          s2b();
        }
        fence_async_smem();
        nb_sync(NB_WG + wg, 128);
        done(it);
        s4(it);
        if (it < 2) s1(it + 2);
      }
      wg_wait<0>();
      if (signaller) mbar_arrive_cluster(rbars + 8 * (BAR_EMPTY2 + 4));
      e4(3);
      PROF(6 + wg);
    }
    }

    if (MODE != 1) {
      float acc[64];
      int s = 0, ph = 0;
#pragma unroll 1
      for (int kb = 0; kb < 16; kb++) {
        mbar_wait(bars + 8 * (BAR_FULL2 + s), ph);
        if (kb == 0) PROF(8 + wg);
        if (warp == 4) PROF2(40 + kb);
        const uint64_t da = mkdesc(sb + g2_a(s) + wg * 8192, 16, 1024, 1);
        const uint64_t db = mkdesc(sb + g2_b(s), 8192, 1024, 1);
        wg_fence();
        wgmma_n128(acc, da, db, kb);
        wgmma_n128(acc, da + 2, db + 128, 1);
        wgmma_n128(acc, da + 4, db + 256, 1);
        wgmma_n128(acc, da + 6, db + 384, 1);
        wg_commit();
        wg_wait<0>();
        if (kb < 16 - NS2 && signaller) mbar_arrive_cluster(rbars + 8 * (BAR_EMPTY2 + s));
        if (++s == NS2) { s = 0; ph ^= 1; }
      }
      wg_wait<0>();
      fence_regs(acc);
      PROF(10 + wg);
      const int lr = lane & 7, lm = lane >> 3;
      const uint32_t wbase = sb + warp * 2048;
      const uint32_t base = wbase + (lr + 8 * (lm & 1)) * 128;
#pragma unroll
      for (int j = 0; j < 16; j += 2) {
        const uint32_t a = base + (j >> 3) * 16384 + ((((j & 7) + (lm >> 1)) ^ lr) << 4);
        stsm4(a, pack_bf16(acc[4 * j], acc[4 * j + 1]), pack_bf16(acc[4 * j + 2], acc[4 * j + 3]),
              pack_bf16(acc[4 * j + 4], acc[4 * j + 5]), pack_bf16(acc[4 * j + 6], acc[4 * j + 7]));
      }
      __syncwarp();
      {
        const int rr = lane >> 4, ck = lane & 7, hf = (lane >> 3) & 1;
        uint4* og = reinterpret_cast<uint4*>(p.out + (size_t)(2 * ((rb2 & 7) * 128 + warp * 16 + rr) + (rb2 >> 3)) * (2 * DM) + DM + cb2 * 128 + hf * 64 + ck * 8);
        uint4 v[8];
#pragma unroll
        for (int i = 0; i < 8; i++) v[i] = lds128(wbase + hf * 16384 + (2 * i + rr) * 128 + ((ck ^ ((2 * i + rr) & 7)) << 4));
#pragma unroll
        for (int i = 0; i < 8; i++) og[(size_t)i * 4 * (2 * DM / 8)] = v[i];
      }
      PROF(12 + wg);
    }
    cluster_sync_all();
  }
}

typedef CUresult (*EncodeFn)(CUtensorMap*, CUtensorMapDataType, cuuint32_t, void*, const cuuint64_t*, const cuuint64_t*,
                             const cuuint32_t*, const cuuint32_t*, CUtensorMapInterleave, CUtensorMapSwizzle,
                             CUtensorMapL2promotion, CUtensorMapFloatOOBfill);

void make_map(EncodeFn enc, CUtensorMap* tm, const void* base, int rank, const cuuint64_t* dims, const cuuint64_t* strides,
              const cuuint32_t* box, CUtensorMapSwizzle swz) {
  cuuint32_t es[5] = {1, 1, 1, 1, 1};
  enc(tm, CU_TENSOR_MAP_DATA_TYPE_BFLOAT16, rank, const_cast<void*>(base), dims, strides, box, es,
      CU_TENSOR_MAP_INTERLEAVE_NONE, swz, CU_TENSOR_MAP_L2_PROMOTION_L2_256B, CU_TENSOR_MAP_FLOAT_OOB_FILL_NONE);
}

}

extern "C" void kernel_launch(void* const* d_in, const int* in_sizes, int n_in, void* d_out, int out_size) {
  static EncodeFn enc = nullptr;
  static bool coresident = true;
  if (!enc) {
    void* fn = nullptr;
    cudaDriverEntryPointQueryResult qr;
    cudaGetDriverEntryPoint("cuTensorMapEncodeTiled", &fn, cudaEnableDefault, &qr);
    enc = (EncodeFn)fn;
    cudaFuncSetAttribute(fused_kernel<0>, cudaFuncAttributeMaxDynamicSharedMemorySize, SMEM_BYTES);
    cudaFuncSetAttribute(fused_kernel<1>, cudaFuncAttributeMaxDynamicSharedMemorySize, SMEM_BYTES);
    cudaFuncSetAttribute(fused_kernel<2>, cudaFuncAttributeMaxDynamicSharedMemorySize, SMEM_BYTES);
    cudaLaunchConfig_t cfg = {};
    cfg.gridDim = dim3(NCTA);
    cfg.blockDim = dim3(NTHREADS);
    cfg.dynamicSmemBytes = SMEM_BYTES;
    cudaLaunchAttribute at;
    at.id = cudaLaunchAttributeClusterDimension;
    at.val.clusterDim.x = 2;
    at.val.clusterDim.y = 1;
    at.val.clusterDim.z = 1;
    cfg.attrs = &at;
    cfg.numAttrs = 1;
    int nclusters = 0;
    if (cudaOccupancyMaxActiveClusters(&nclusters, fused_kernel<0>, &cfg) == cudaSuccess) coresident = nclusters >= NCTA / 2;
    (void)cudaGetLastError();
  }
  CUtensorMap tmX, tmW, tmWo, tmQ, tmXh, tmWh;
  {
    cuuint64_t dims[3] = {1024, 2, 1024};
    cuuint64_t str[2] = {2048, 4096};
    cuuint32_t box[3] = {64, 1, 128};
    make_map(enc, &tmX, d_in[6], 3, dims, str, box, CU_TENSOR_MAP_SWIZZLE_128B);
  }
  {
    cuuint64_t dims[3] = {1024, 1024, 3};
    cuuint64_t str[2] = {6144, 2048};
    cuuint32_t box[3] = {64, 32, 3};
    make_map(enc, &tmW, d_in[7], 3, dims, str, box, CU_TENSOR_MAP_SWIZZLE_128B);
  }
  {
    cuuint64_t dims[3] = {64, 1024, 16};
    cuuint64_t str[2] = {2048, 128};
    cuuint32_t box[3] = {64, 64, 2};
    make_map(enc, &tmWo, d_in[8], 3, dims, str, box, CU_TENSOR_MAP_SWIZZLE_128B);
  }
  {
    cuuint64_t dims[5] = {1024, 2, 4, 4, 64};
    cuuint64_t str[4] = {2048, 8 * 2048, 2 * 2048, 32 * 2048};
    cuuint32_t box[5] = {16, 2, 4, 4, 4};
    make_map(enc, &tmQ, d_in[0], 5, dims, str, box, CU_TENSOR_MAP_SWIZZLE_NONE);
  }
  {
    cuuint64_t dims[4] = {1024, 256, 2, 4};
    cuuint64_t str[3] = {4096, 2048, 256 * 4096};
    cuuint32_t box[4] = {64, 8, 2, 4};
    make_map(enc, &tmXh, d_in[6], 4, dims, str, box, CU_TENSOR_MAP_SWIZZLE_128B);
  }
  {
    cuuint64_t dims[3] = {64, 1024, 48};
    cuuint64_t str[2] = {6144, 128};
    cuuint32_t box[3] = {64, 64, 4};
    make_map(enc, &tmWh, d_in[7], 3, dims, str, box, CU_TENSOR_MAP_SWIZZLE_128B);
  }
  Params p;
  p.q = (const __nv_bfloat16*)d_in[0];
  p.k = (const __nv_bfloat16*)d_in[1];
  p.v = (const __nv_bfloat16*)d_in[2];
  p.shift_k = (const __nv_bfloat16*)d_in[3];
  p.ssm_k = (const __nv_bfloat16*)d_in[4];
  p.ssm_D = (const __nv_bfloat16*)d_in[5];
  p.x = (const __nv_bfloat16*)d_in[6];
  p.w = (const __nv_bfloat16*)d_in[7];
  p.wo = (const __nv_bfloat16*)d_in[8];
  p.out = (__nv_bfloat16*)d_out;
  if (coresident) {
    fused_kernel<0><<<NCTA, NTHREADS, SMEM_BYTES>>>(p, tmX, tmW, tmWo, tmQ, tmXh, tmWh);
  } else {
    fused_kernel<0><<<4, NTHREADS, SMEM_BYTES>>>(p, tmX, tmW, tmWo, tmQ, tmXh, tmWh);
    fused_kernel<1><<<NCTA, NTHREADS, SMEM_BYTES>>>(p, tmX, tmW, tmWo, tmQ, tmXh, tmWh);
    fused_kernel<2><<<NCTA, NTHREADS, SMEM_BYTES>>>(p, tmX, tmW, tmWo, tmQ, tmXh, tmWh);
  }
}
```

```cpp
#include <cuda_runtime.h>
#include <cuda.h>
#include <cuda_bf16.h>
#include <stdint.h>

namespace {

constexpr int SEQ = 2048;
constexpr int DM = 1024;
constexpr int NCTA = 132;
constexpr int NTHREADS = 384;

constexpr int STG1A = 32768;
constexpr int NS1A = 3;
constexpr int STG1B = 12288;
constexpr int NS1B = 5;
constexpr int OFF_1B = NS1A * STG1A;
constexpr int STG2 = 32768;
constexpr int NS2 = 5;
constexpr int STGH = 73728;
constexpr int OFF_VP = 0;
constexpr int OFF_KH = 1 * STG2;
constexpr int OFF_OP = 2 * STG2;
constexpr int OFF_Q = 3 * STG2;
constexpr int T_A4 = 0, T_TW = 16384, T_B2 = 24576, T_A1 = 28672, T_END = 32768;
constexpr int OFF_U = 163840;
constexpr int OFF_H = OFF_U + 32768;
constexpr int OFF_T = OFF_U - T_END;
constexpr int OFF_LAND = 4 * STG2;
constexpr int OFF_BAR = OFF_H + 32768;
constexpr int OFF_SC = OFF_BAR + 512;
constexpr int OFF_L0 = OFF_BAR + 1024;
constexpr int SMEM_BYTES = OFF_L0 + 2048;
static_assert(OFF_T + T_A1 == OFF_1B + NS1B * STG1B && OFF_T + T_TW == OFF_1B + 4 * STG1B && OFF_LAND == OFF_T + T_A4, "layout");
static_assert(3 * STGH <= OFF_BAR && SMEM_BYTES <= 232448, "smem");

constexpr int BAR_FULLA = 0;
constexpr int BAR_EMPTYA = 3;
constexpr int BAR_FULLB = 6;
constexpr int BAR_EMPTYB = 11;
constexpr int BAR_FULL2 = 16;
constexpr int BAR_EMPTY2 = 21;
constexpr int BAR_T = 26;
constexpr int BAR_UH = 27;
constexpr int BAR_LFREE = 28;
constexpr int BAR_LAND = 29;
constexpr int BAR_U = 30;
constexpr int BAR_Q = 31;
constexpr int BAR_STG = 32;
constexpr int BAR_DEAD = 33;
constexpr int BAR_X = 35;
constexpr int BAR_REL = 36;

constexpr int NB_G1DONE = 1;
constexpr int NB_OREADY = 2;
constexpr int NB_WG = 4;
constexpr int NB_HELP3 = 6;
constexpr int NB_FIRST = 7;

#define PACE 480u
#define PF0 20
#define LOOKAHEAD 6
#define SCHED 1
#define REG_MATH 224
#define REG_HELP 56
constexpr int SPIN_LIMIT = 1 << 20;

__device__ __align__(1024) __nv_bfloat16 g_o[SEQ * DM];
__device__ uint32_t g_flag_o[256];
__device__ uint32_t g_flag_h[4];
__device__ uint4 g_halo[128 * 128];
__device__ __align__(128) const uint32_t g_tab[T_END / 4] = {
0x3c003c00,0x3bf13bff,0,0xafd6a648,0x3c003c00,0x3b993bce,0,0xb505b303,0x3c003c00,0x3af63b50,0,0xb7e3b67c,
0x3c003c00,0x3a0f3a8a,0,0xb93ab89b,0x3bc33bfe,0x3b773bfa,0xb3c6aa48,0xb5c2acb5,0x3a6d3b3b,0x389b3a4f,0xb8c4b6d7,0xba8ab8ec,
0x381d395f,0x26483505,0xbaddb9ed,0xbbffbb99,0x30b23564,0xb848b444,0xbbeabb88,0xbac2bbb6,0x3b0e3bf6,0x3a8a3bf1,0xb78bae46,0xb89bafd6,
0x34a53913,0xa6483732,0xbba8ba2f,0xbbffbb25,0xb78bae46,0xbac2b7e3,0xbb0ebbf6,0xb848baf6,0xbba8ba2f,0xbb50bbfa,0xb4a5b913,0x367cacb5,
0x39ed3bea,0x393a3be2,0xb95fb0b2,0xba0fb179,0xb56433c6,0xb8ec2648,0xbb88bbc3,0xba4fbbff,0xbbfeba6d,0xbb25bbce,0xaa48b8c4,0x3732b303,
0xb6d7badd,0x3444b67c,0x3b3b381d,0x3bb63b50,0x38723bd9,0x37323bce,0xbaa7b23e,0xbb25b303,0xbaa7b23e,0xbbb6b67c,0xb872bbd9,0xb444bb50,
0xb872bbd9,0xacb5ba8a,0x3aa7323e,0x3bfa389b,0x3aa7323e,0x3bf139cb,0x38723bd9,0xafd63984,0x35643bc3,0x33033bb6,0xbb88b3c6,0xbbceb444,
0xbbfeb8c4,0xbb77ba0f,0x2a48ba6d,0x35c2b93a,0x36d7b81d,0x3a8aafd6,0x3b3b3add,0x389b3bf1,0x395f3bea,0x26483b25,0xb9ed30b2,0xbbffb732,
0x2e463ba8,0xa6483b99,0xbbf6b4a5,0xbbffb505,0xba2fbb0e,0xb848bbb6,0x3913b78b,0x3ac2b444,0x3bf634a5,0x3b50393a,0x2e463ba8,0xb67c3a0f,
0xb913378b,0xbbe2afd6,0xba2fbb0e,0xb179bbf1,0xb0b23b88,0xb4443b77,0xbbeab564,0xbbb6b5c2,0xb3c6bbfe,0x2cb5bbe2,0x3bc3aa48,0x3bfa3179,
0x38c43b3b,0x2fd63bff,0xba6d36d7,0xbbf12648,0xbaddb95f,0xb505bbce,0x381db9ed,0x3b99b303,0xb61f3b64,0xb7e33b50,0xbb64b61f,0xbaf6b67c,
0x361fbb64,0x393aba8a,0x3b64361f,0x3a0f389b,0xb61f3b64,0xba4f3984,0xbb64b61f,0xb8ecb9cb,0x361fbb64,0x3b25b848,0x3b64361f,0x37323ac2,
0xb8c43b3b,0xb9843b25,0xba6db6d7,0xb9cbb732,0x3addb95f,0x3bceb7e3,0x381d39ed,0x33033af6,0xbbea3564,0xbb77acb5,0xb0b2bb88,0x35c2bbfa,
0x3bc32a48,0x389b38ec,0xb3c63bfe,0xba8a3a4f,0xba2f3b0e,0xbac23af6,0xb913b78b,0xb848b7e3,0x3bf6b4a5,0x3b50acb5,0xae463ba8,0xb67c3bfa,
0xb913b78b,0xb179ba4f,0x3a2fbb0e,0x3be2b8ec,0xae463ba8,0xb9cb3b99,0xbbf634a5,0xb984b505,0xbb3b3add,0xbb993ac2,0xb6d7b81d,0xb505b848,
0x39ed30b2,0x37e335c2,0xb95f3bea,0xbaf63b77,0x3564bbc3,0x3a0fbbe2,0x3b88b3c6,0x393a3179,0xbbfe38c4,0xba4f2648,0xaa48ba6d,0x38ecbbff,
0xbbd93aa7,0xbbfa3a8a,0xb23eb872,0xacb5b89b,0x323e3872,0xafd639cb,0xbbd93aa7,0xbbf13984,0x3bd9baa7,0x3b99b848,0x323e3872,0xb5053ac2,
0xb23eb872,0x37e3bb77,0x3bd9baa7,0x3af6b5c2,0xbbfe3a6d,0xbbe23a4f,0x2a48b8c4,0x3179b8ec,0xb6d73add,0xb9843b99,0xbb3b381d,0xb9cb3505,
0x395fb0b2,0x33033444,0xb9ed3bea,0xbbce3bb6,0x3b88bbc3,0x3b77b93a,0x356433c6,0xb5c23a0f,0xbba83a2f,0xbb503a0f,0x34a5b913,0x367cb93a,
0xbb0e3bf6,0xbbe23bf1,0xb78b2e46,0xb179afd6,0xb4a53913,0xb9cb3b25,0xbba83a2f,0xb9843732,0x378bae46,0xb30337e3,0xbb0e3bf6,0xbbce3af6,
0xbadd39ed,0xba4f39cb,0x381db95f,0x38ecb984,0xbbea3b88,0xbb253ac2,0x30b2b564,0x3732b848,0xbbc33bfe,0xbbb63b77,0xb3c62a48,0x3444b5c2,
0xba6d3b3b,0xbbfa3be2,0xb8c436d7,0x2cb5b179,0xb9a839a8,0xb8ec3984,0x39a8b9a8,0x3a4fb9cb,0xb9a839a8,0xb7323848,0x39a8b9a8,0x3b25bac2,
0xb9a839a8,0xb44435c2,0x39a8b9a8,0x3bb6bb77,0xb9a839a8,0xacb53179,0x39a8b9a8,0x3bfabbe2,0xb81d395f,0xb67c393a,0x3addb9ed,0x3b50ba0f,
0xb0b23564,0x31792fd6,0x3beabb88,0x3be2bbf1,0x33c6aa48,0x3984b732,0x3bc3bbfe,0x39cbbb25,0x38c4b6d7,0x3bcebaf6,0x3a6dbb3b,0x3303b7e3,
0xb4a53913,0xb17938ec,0x3ba8ba2f,0x3be2ba4f,0x378bae46,0x39cbb505,0x3b0ebbf6,0x3984bb99,0x3ba8ba2f,0x3bcebbb6,0x34a5b913,0xb303b444,
0x3b0ebbf6,0x35c2ba0f,0xb78b2e46,0xbb77393a,0xaa4838c4,0x2cb5389b,0x3bfeba6d,0x3bfaba8a,0x3b3bb81d,0x3bf1b984,0x36d7badd,0x2fd6b9cb,
0x39edbbea,0x3505bac2,0xb95f30b2,0xbb993848,0xb564b3c6,0xbaf635c2,0xbb883bc3,0xb7e33b77,0x323e3872,0x35053848,0x3bd9baa7,0x3b99bac2,
0x3bd9baa7,0x3af6bb77,0xb23eb872,0xb7e3b5c2,0xb23eb872,0xb93ab179,0xbbd93aa7,0xba0f3be2,0xbbd93aa7,0xb8ec3bff,0x323e3872,0x3a4fa648,
0x36d7381d,0x384837e3,0x3b3bbadd,0x3ac2baf6,0x395fbbea,0x367cbbfa,0xb9edb0b2,0xbb502cb5,0xbb8833c6,0xbbe238ec,0xb5643bc3,0x31793a4f,
0x2a483a6d,0x39843505,0x3bfeb8c4,0x39cbbb99,0x3913378b,0x39cb3732,0x3a2fbb0e,0x3984bb25,0x2e46bba8,0xb303baf6,0xbbf634a5,0xbbce37e3,
0xba2f3b0e,0xb5c23bfa,0x3913378b,0x3b772cb5,0x3bf6b4a5,0x3a8aba4f,0x2e46bba8,0xb89bb8ec,0x3a6d36d7,0x3af6367c,0x38c4bb3b,0x37e3bb50,
0xb81db9ed,0xba0fb89b,0xbadd395f,0xb93a3a8a,0x30b23b88,0x38ec39cb,0x3beab564,0x3a4fb984,0x33c6bbfe,0xb732bac2,0xbbc3aa48,0xbb253848,
0x3b64361f,0x3bb635c2,0x361fbb64,0x3444bb77,0xbb64b61f,0xbbfab179,0xb61f3b64,0xacb53be2,0x3b64361f,0x3bf1a648,0x361fbb64,0xafd6bbff,
0xbb64b61f,0xbb993303,0xb61f3b64,0x35053bce,0x3bea3564,0x3bff3505,0x30b2bb88,0x2648bb99,0xbbc32a48,0xbac23444,0x33c63bfe,0x38483bb6,
0x3a6db6d7,0x367cba0f,0xb8c4bb3b,0xbb50b93a,0xb81d39ed,0x31793bf1,0x3add395f,0x3be22fd6,0x3bf634a5,0x3bce3444,0xae46bba8,0xb303bbb6,
0xb913378b,0xb5c2393a,0x3a2f3b0e,0x3b773a0f,0xae46bba8,0xb89bbbf1,0xbbf6b4a5,0xba8a2fd6,0x3a2f3b0e,0x3bff3732,0x3913b78b,0xa648bb25,
0x3b8833c6,0x3b253303,0xb564bbc3,0xb732bbce,0xaa483a6d,0x34443b50,0x3bfe38c4,0x3bb6367c,0xbb3bbadd,0xbbfab89b,0xb6d7381d,0x2cb53a8a,
0x39edb0b2,0x2fd6b984,0xb95fbbea,0xbbf1b9cb,0x3aa7323e,0x3a0f3179,0xb872bbd9,0xb93abbe2,0x38723bd9,0x3a4f3bff,0x3aa7323e,0x38eca648,
0xbaa7b23e,0xb7323303,0x38723bd9,0x3b253bce,0xb872bbd9,0xbbb6bb50,0xbaa7b23e,0xb444367c,0x395f30b2,0x389b2fd6,0xb9edbbea,0xba8abbf1,
0x3b883bc3,0x3bff3b25,0x3564b3c6,0x2648b732,0x2a4838c4,0x38483af6,0x3bfe3a6d,0x3ac237e3,0xbb3bb81d,0xb67c2cb5,0x36d73add,0x3b503bfa,
0x378b2e46,0x35c22cb5,0xbb0ebbf6,0xbb77bbfa,0x3ba83a2f,0x3a8a38ec,0xb4a5b913,0xb89bba4f,0x3b0e3bf6,0x3bff3b99,0x378b2e46,0xa648b505,
0x34a53913,0x3ac23bb6,0x3ba83a2f,0x38483444,0x33c62a48,0x2fd62648,0xbbc3bbfe,0xbbf1bbff,0x38c436d7,0x35053303,0xba6dbb3b,0xbb99bbce,
0x3add39ed,0x37e3367c,0xb81db95f,0xbaf6bb50,0x3bea3b88,0x393a389b,0xb0b2b564,0xba0fba8a,0x3c003c00,0xbbf1bbff,0,0x2fd62648,
0x3c003c00,0xbb99bbce,0,0x35053303,0x3c003c00,0xbaf6bb50,0,0x37e3367c,0x3c003c00,0xba0fba8a,0,0x393a389b,
0x3bc33bfe,0xbb77bbfa,0xb3c6aa48,0x35c22cb5,0x3a6d3b3b,0xb89bba4f,0xb8c4b6d7,0x3a8a38ec,0x381d395f,0xa648b505,0xbaddb9ed,0x3bff3b99,
0x30b23564,0x38483444,0xbbeabb88,0x3ac23bb6,0x3b0e3bf6,0xba8abbf1,0xb78bae46,0x389b2fd6,0x34a53913,0x2648b732,0xbba8ba2f,0x3bff3b25,
0xb78bae46,0x3ac237e3,0xbb0ebbf6,0x38483af6,0xbba8ba2f,0x3b503bfa,0xb4a5b913,0xb67c2cb5,0x39ed3bea,0xb93abbe2,0xb95fb0b2,0x3a0f3179,
0xb56433c6,0x38eca648,0xbb88bbc3,0x3a4f3bff,0xbbfeba6d,0x3b253bce,0xaa48b8c4,0xb7323303,0xb6d7badd,0xb444367c,0x3b3b381d,0xbbb6bb50,
0x38723bd9,0xb732bbce,0xbaa7b23e,0x3b253303,0xbaa7b23e,0x3bb6367c,0xb872bbd9,0x34443b50,0xb872bbd9,0x2cb53a8a,0x3aa7323e,0xbbfab89b,
0x3aa7323e,0xbbf1b9cb,0x38723bd9,0x2fd6b984,0x35643bc3,0xb303bbb6,0xbb88b3c6,0x3bce3444,0xbbfeb8c4,0x3b773a0f,0x2a48ba6d,0xb5c2393a,
0x36d7b81d,0xba8a2fd6,0x3b3b3add,0xb89bbbf1,0x395f3bea,0xa648bb25,0xb9ed30b2,0x3bff3732,0x2e463ba8,0x2648bb99,0xbbf6b4a5,0x3bff3505,
0xba2fbb0e,0x38483bb6,0x3913b78b,0xbac23444,0x3bf634a5,0xbb50b93a,0x2e463ba8,0x367cba0f,0xb913378b,0x3be22fd6,0xba2fbb0e,0x31793bf1,
0xb0b23b88,0x3444bb77,0xbbeab564,0x3bb635c2,0xb3c6bbfe,0xacb53be2,0x3bc3aa48,0xbbfab179,0x38c43b3b,0xafd6bbff,0xba6d36d7,0x3bf1a648,
0xbaddb95f,0x35053bce,0x381db9ed,0xbb993303,0xb61f3b64,0x37e3bb50,0xbb64b61f,0x3af6367c,0x361fbb64,0xb93a3a8a,0x3b64361f,0xba0fb89b,
0xb61f3b64,0x3a4fb984,0xbb64b61f,0x38ec39cb,0x361fbb64,0xbb253848,0x3b64361f,0xb732bac2,0xb8c43b3b,0x3984bb25,0xba6db6d7,0x39cb3732,
0x3addb95f,0xbbce37e3,0x381d39ed,0xb303baf6,0xbbea3564,0x3b772cb5,0xb0b2bb88,0xb5c23bfa,0x3bc32a48,0xb89bb8ec,0xb3c63bfe,0x3a8aba4f,
0xba2f3b0e,0x3ac2baf6,0xb913b78b,0x384837e3,0x3bf6b4a5,0xbb502cb5,0xae463ba8,0x367cbbfa,0xb913b78b,0x31793a4f,0x3a2fbb0e,0xbbe238ec,
0xae463ba8,0x39cbbb99,0xbbf634a5,0x39843505,0xbb3b3add,0x3b99bac2,0xb6d7b81d,0x35053848,0x39ed30b2,0xb7e3b5c2,0xb95f3bea,0x3af6bb77,
0x3564bbc3,0xba0f3be2,0x3b88b3c6,0xb93ab179,0xbbfe38c4,0x3a4fa648,0xaa48ba6d,0xb8ec3bff,0xbbd93aa7,0x3bfaba8a,0xb23eb872,0x2cb5389b,
0x323e3872,0x2fd6b9cb,0xbbd93aa7,0x3bf1b984,0x3bd9baa7,0xbb993848,0x323e3872,0x3505bac2,0xb23eb872,0xb7e33b77,0x3bd9baa7,0xbaf635c2,
0xbbfe3a6d,0x3be2ba4f,0x2a48b8c4,0xb17938ec,0xb6d73add,0x3984bb99,0xbb3b381d,0x39cbb505,0x395fb0b2,0xb303b444,0xb9ed3bea,0x3bcebbb6,
0x3b88bbc3,0xbb77393a,0x356433c6,0x35c2ba0f,0xbba83a2f,0x3b50ba0f,0x34a5b913,0xb67c393a,0xbb0e3bf6,0x3be2bbf1,0xb78b2e46,0x31792fd6,
0xb4a53913,0x39cbbb25,0xbba83a2f,0x3984b732,0x378bae46,0x3303b7e3,0xbb0e3bf6,0x3bcebaf6,0xbadd39ed,0x3a4fb9cb,0x381db95f,0xb8ec3984,
0xbbea3b88,0x3b25bac2,0x30b2b564,0xb7323848,0xbbc33bfe,0x3bb6bb77,0xb3c62a48,0xb44435c2,0xba6d3b3b,0x3bfabbe2,0xb8c436d7,0xacb53179,
0xb9a839a8,0x38ecb984,0x39a8b9a8,0xba4f39cb,0xb9a839a8,0x3732b848,0x39a8b9a8,0xbb253ac2,0xb9a839a8,0x3444b5c2,0x39a8b9a8,0xbbb63b77,
0xb9a839a8,0x2cb5b179,0x39a8b9a8,0xbbfa3be2,0xb81d395f,0x367cb93a,0x3addb9ed,0xbb503a0f,0xb0b23564,0xb179afd6,0x3beabb88,0xbbe23bf1,
0x33c6aa48,0xb9843732,0x3bc3bbfe,0xb9cb3b25,0x38c4b6d7,0xbbce3af6,0x3a6dbb3b,0xb30337e3,0xb4a53913,0x3179b8ec,0x3ba8ba2f,0xbbe23a4f,
0x378bae46,0xb9cb3505,0x3b0ebbf6,0xb9843b99,0x3ba8ba2f,0xbbce3bb6,0x34a5b913,0x33033444,0x3b0ebbf6,0xb5c23a0f,0xb78b2e46,0x3b77b93a,
0xaa4838c4,0xacb5b89b,0x3bfeba6d,0xbbfa3a8a,0x3b3bb81d,0xbbf13984,0x36d7badd,0xafd639cb,0x39edbbea,0xb5053ac2,0xb95f30b2,0x3b99b848,
0xb564b3c6,0x3af6b5c2,0xbb883bc3,0x37e3bb77,0x323e3872,0xb505b848,0x3bd9baa7,0xbb993ac2,0x3bd9baa7,0xbaf63b77,0xb23eb872,0x37e335c2,
0xb23eb872,0x393a3179,0xbbd93aa7,0x3a0fbbe2,0xbbd93aa7,0x38ecbbff,0x323e3872,0xba4f2648,0x36d7381d,0xb848b7e3,0x3b3bbadd,0xbac23af6,
0x395fbbea,0xb67c3bfa,0xb9edb0b2,0x3b50acb5,0xbb8833c6,0x3be2b8ec,0xb5643bc3,0xb179ba4f,0x2a483a6d,0xb984b505,0x3bfeb8c4,0xb9cb3b99,
0x3913378b,0xb9cbb732,0x3a2fbb0e,0xb9843b25,0x2e46bba8,0x33033af6,0xbbf634a5,0x3bceb7e3,0xba2f3b0e,0x35c2bbfa,0x3913378b,0xbb77acb5,
0x3bf6b4a5,0xba8a3a4f,0x2e46bba8,0x389b38ec,0x3a6d36d7,0xbaf6b67c,0x38c4bb3b,0xb7e33b50,0xb81db9ed,0x3a0f389b,0xbadd395f,0x393aba8a,
0x30b23b88,0xb8ecb9cb,0x3beab564,0xba4f3984,0x33c6bbfe,0x37323ac2,0xbbc3aa48,0x3b25b848,0x3b64361f,0xbbb6b5c2,0x361fbb64,0xb4443b77,
0xbb64b61f,0x3bfa3179,0xb61f3b64,0x2cb5bbe2,0x3b64361f,0xbbf12648,0x361fbb64,0x2fd63bff,0xbb64b61f,0x3b99b303,0xb61f3b64,0xb505bbce,
0x3bea3564,0xbbffb505,0x30b2bb88,0xa6483b99,0xbbc32a48,0x3ac2b444,0x33c63bfe,0xb848bbb6,0x3a6db6d7,0xb67c3a0f,0xb8c4bb3b,0x3b50393a,
0xb81d39ed,0xb179bbf1,0x3add395f,0xbbe2afd6,0x3bf634a5,0xbbceb444,0xae46bba8,0x33033bb6,0xb913378b,0x35c2b93a,0x3a2f3b0e,0xbb77ba0f,
0xae46bba8,0x389b3bf1,0xbbf6b4a5,0x3a8aafd6,0x3a2f3b0e,0xbbffb732,0x3913b78b,0x26483b25,0x3b8833c6,0xbb25b303,0xb564bbc3,0x37323bce,
0xaa483a6d,0xb444bb50,0x3bfe38c4,0xbbb6b67c,0xbb3bbadd,0x3bfa389b,0xb6d7381d,0xacb5ba8a,0x39edb0b2,0xafd63984,0xb95fbbea,0x3bf139cb,
0x3aa7323e,0xba0fb179,0xb872bbd9,0x393a3be2,0x38723bd9,0xba4fbbff,0x3aa7323e,0xb8ec2648,0xbaa7b23e,0x3732b303,0x38723bd9,0xbb25bbce,
0xb872bbd9,0x3bb63b50,0xbaa7b23e,0x3444b67c,0x395f30b2,0xb89bafd6,0xb9edbbea,0x3a8a3bf1,0x3b883bc3,0xbbffbb25,0x3564b3c6,0xa6483732,
0x2a4838c4,0xb848baf6,0x3bfe3a6d,0xbac2b7e3,0xbb3bb81d,0x367cacb5,0x36d73add,0xbb50bbfa,0x378b2e46,0xb5c2acb5,0xbb0ebbf6,0x3b773bfa,
0x3ba83a2f,0xba8ab8ec,0xb4a5b913,0x389b3a4f,0x3b0e3bf6,0xbbffbb99,0x378b2e46,0x26483505,0x34a53913,0xbac2bbb6,0x3ba83a2f,0xb848b444,
0x33c62a48,0xafd6a648,0xbbc3bbfe,0x3bf13bff,0x38c436d7,0xb505b303,0xba6dbb3b,0x3b993bce,0x3add39ed,0xb7e3b67c,0xb81db95f,0x3af63b50,
0x3bea3b88,0xb93ab89b,0xb0b2b564,0x3a0f3a8a,0x3c003c00,0x38ec3984,0,0xba4fb9cb,0x3c003c00,0x37323848,0,0xbb25bac2,
0x3c003c00,0x344435c2,0,0xbbb6bb77,0x3c003c00,0x2cb53179,0,0xbbfabbe2,0xb3c6aa48,0xbb50ba0f,0xbbc3bbfe,0xb67cb93a,
0xb8c4b6d7,0xbbe2bbf1,0xba6dbb3b,0x3179afd6,0xbaddb9ed,0xb9cbbb25,0xb81db95f,0x39843732,0xbbeabb88,0xb303b7e3,0xb0b2b564,0x3bce3af6,
0xbb0ebbf6,0xb179b8ec,0x378b2e46,0x3be23a4f,0xb4a5b913,0x39cb3505,0x3ba83a2f,0x39843b99,0x378b2e46,0x3bce3bb6,0x3b0e3bf6,0xb3033444,
0x3ba83a2f,0x35c23a0f,0x34a53913,0xbb77b93a,0x395f30b2,0x3bfa3a8a,0x39ed3bea,0xacb5389b,0x3b883bc3,0x2fd639cb,0xb56433c6,0xbbf1b984,
0x2a4838c4,0xbb99b848,0xbbfeba6d,0xb505bac2,0xbb3bb81d,0xb7e3bb77,0xb6d7badd,0x3af635c2,0x38723bd9,0xb5053848,0xbaa7b23e,0xbb99bac2,
0xbaa7b23e,0xbaf6bb77,0xb872bbd9,0x37e3b5c2,0xb872bbd9,0x393ab179,0x3aa7323e,0x3a0f3be2,0x3aa7323e,0x38ec3bff,0x38723bd9,0xba4fa648,
0xbb88b3c6,0xbac2baf6,0xb564bbc3,0x3848b7e3,0x2a48ba6d,0x3b502cb5,0x3bfe38c4,0x367c3bfa,0x3b3b3add,0xb1793a4f,0xb6d7381d,0xbbe2b8ec,
0xb9ed30b2,0xb9cbbb99,0xb95fbbea,0x3984b505,0xae46bba8,0x39cbb732,0x3bf634a5,0x39843b25,0x3a2f3b0e,0xb3033af6,0xb913378b,0xbbceb7e3,
0xbbf6b4a5,0xb5c2bbfa,0xae46bba8,0x3b77acb5,0x3913b78b,0x3a8a3a4f,0x3a2f3b0e,0xb89b38ec,0x3bea3564,0x37e33b50,0xb0b23b88,0xbaf6367c,
0xbbc32a48,0xb93aba8a,0xb3c6bbfe,0x3a0fb89b,0x3a6db6d7,0x3a4f3984,0x38c43b3b,0xb8ec39cb,0xb81d39ed,0xbb25b848,0xbaddb95f,0x3732bac2,
0xb61f3b64,0xbbb635c2,0xbb64b61f,0xb444bb77,0x361fbb64,0x3bfab179,0x3b64361f,0x2cb53be2,0xb61f3b64,0xbbf1a648,0xbb64b61f,0x2fd6bbff,
0x361fbb64,0x3b993303,0x3b64361f,0xb5053bce,0xba6db6d7,0xa648bb99,0x38c4bb3b,0x3bffb505,0x381d39ed,0xb8483bb6,0xbadd395f,0xbac2b444,
0xb0b2bb88,0x3b50b93a,0x3beab564,0x367c3a0f,0xb3c63bfe,0xbbe22fd6,0xbbc3aa48,0x3179bbf1,0x3a2fbb0e,0x3bceb444,0x3913378b,0xb3033bb6,
0xbbf634a5,0xb5c2b93a,0x2e46bba8,0x3b77ba0f,0x3913378b,0xb89b3bf1,0xba2f3b0e,0xba8aafd6,0x2e46bba8,0x3bffb732,0x3bf6b4a5,0xa6483b25,
0x36d7381d,0xb7323bce,0xbb3b3add,0xbb253303,0x395fbbea,0x3bb6b67c,0x39ed30b2,0xb4443b50,0xbb8833c6,0x2cb5ba8a,0x3564bbc3,0x3bfab89b,
0x2a483a6d,0xbbf139cb,0xbbfe38c4,0xafd6b984,0xbbd93aa7,0xba0f3179,0xb23eb872,0x393abbe2,0x323e3872,0xba4f3bff,0xbbd93aa7,0xb8eca648,
0x3bd9baa7,0x37323303,0x323e3872,0xbb253bce,0xb23eb872,0x3bb6bb50,0x3bd9baa7,0x3444367c,0x2a48b8c4,0x3a8abbf1,0x3bfeba6d,0x389bafd6,
0xbb3b381d,0xa648b732,0x36d7badd,0x3bffbb25,0xb9ed3bea,0xbac237e3,0xb95f30b2,0x3848baf6,0x356433c6,0xbb503bfa,0xbb883bc3,0xb67cacb5,
0x3ba8ba2f,0x35c2acb5,0xb4a53913,0xbb773bfa,0x3b0ebbf6,0x3a8ab8ec,0x378bae46,0xb89b3a4f,0x34a5b913,0x3bffbb99,0x3ba8ba2f,0xa6483505,
0xb78b2e46,0x3ac2bbb6,0x3b0ebbf6,0x3848b444,0xb81d395f,0xbbf13bff,0xbadd39ed,0xafd62648,0xb0b23564,0xbb993bce,0xbbea3b88,0xb5053303,
0x33c6aa48,0xbaf63b50,0xbbc33bfe,0xb7e3367c,0x38c4b6d7,0xba0f3a8a,0xba6d3b3b,0xb93a389b,0xb9a839a8,0x2fd6a648,0x39a8b9a8,0x3bf1bbff,
0xb9a839a8,0x3505b303,0x39a8b9a8,0x3b99bbce,0xb9a839a8,0x37e3b67c,0x39a8b9a8,0x3af6bb50,0xb9a839a8,0x393ab89b,0x39a8b9a8,0x3a0fba8a,
0x3addb9ed,0x3b77bbfa,0x381db95f,0xb5c22cb5,0x3beabb88,0x389bba4f,0x30b2b564,0xba8a38ec,0x3bc3bbfe,0x2648b505,0xb3c62a48,0xbbff3b99,
0x3a6dbb3b,0xb8483444,0xb8c436d7,0xbac23bb6,0x34a5b913,0xb89b2fd6,0xbba83a2f,0xba8a3bf1,0xb78b2e46,0xbbff3b25,0xbb0e3bf6,0x26483732,
0xbba83a2f,0xb8483af6,0xb4a53913,0x3ac2b7e3,0xbb0e3bf6,0x367c2cb5,0x378bae46,0x3b50bbfa,0xbbfe3a6d,0xb93a3be2,0xaa4838c4,0x3a0fb179,
0xb6d73add,0x38ec2648,0x3b3bb81d,0x3a4fbbff,0x395fb0b2,0x3b25bbce,0x39edbbea,0xb732b303,0x3b88bbc3,0xb444b67c,0xb564b3c6,0xbbb63b50,
0x323e3872,0x3b25b303,0x3bd9baa7,0x3732bbce,0x3bd9baa7,0x3444bb50,0xb23eb872,0xbbb6367c,0xb23eb872,0xbbfa389b,0xbbd93aa7,0xacb53a8a,
0xbbd93aa7,0x2fd63984,0x323e3872,0x3bf1b9cb,0x3b3bbadd,0x3303bbb6,0xb6d7b81d,0xbbce3444,0xb9edb0b2,0xbb773a0f,0xb95f3bea,0x35c2393a,
0xb5643bc3,0x3a8a2fd6,0x3b88b3c6,0x389bbbf1,0x3bfeb8c4,0x2648bb25,0xaa48ba6d,0xbbff3732,0xb913b78b,0xbbff3505,0xba2f3b0e,0x26483b99,
0xae463ba8,0x3ac23444,0x3bf6b4a5,0x3848bbb6,0x3a2fbb0e,0xb67cba0f,0xb913b78b,0xbb50393a,0xbbf634a5,0xb1793bf1,0xae463ba8,0x3be2afd6,
0xb8c43b3b,0x34443b77,0x3a6d36d7,0x3bb6b5c2,0x3addb95f,0xacb5bbe2,0xb81db9ed,0xbbfa3179,0xbbea3564,0xafd63bff,0x30b23b88,0x3bf12648,
0x3bc32a48,0x3505bbce,0x33c6bbfe,0xbb99b303,0x3b64361f,0x3af6b67c,0x361fbb64,0xb7e3bb50,0xbb64b61f,0xba0f389b,0xb61f3b64,0x393a3a8a,
0x3b64361f,0x38ecb9cb,0x361fbb64,0xba4fb984,0xbb64b61f,0xb7323ac2,0xb61f3b64,0x3b253848,0x30b2bb88,0xb984bb25,0xbbeab564,0xb9cb3732,
0x33c63bfe,0x3bce37e3,0x3bc3aa48,0x3303baf6,0xb8c4bb3b,0xbb772cb5,0xba6d36d7,0x35c23bfa,0x3add395f,0x389bb8ec,0x381db9ed,0xba8aba4f,
0xbbf6b4a5,0xb84837e3,0x2e463ba8,0x3ac23af6,0x3913b78b,0xb67cbbfa,0xba2fbb0e,0xbb50acb5,0x2e463ba8,0x3be238ec,0x3bf634a5,0x3179ba4f,
0xba2fbb0e,0xb9843505,0xb913378b,0x39cb3b99,0x35643bc3,0x3b993ac2,0x3b8833c6,0x3505b848,0xbbfeb8c4,0xb7e335c2,0xaa483a6d,0x3af63b77,
0x36d7b81d,0xba0fbbe2,0xbb3bbadd,0xb93a3179,0x395f3bea,0x3a4f2648,0x39edb0b2,0xb8ecbbff,0x3aa7323e,0x2cb5b89b,0xb872bbd9,0xbbfaba8a,
0x38723bd9,0x3bf13984,0x3aa7323e,0xafd6b9cb,0xbaa7b23e,0x35053ac2,0x38723bd9,0x3b993848,0xb872bbd9,0xbaf6b5c2,0xbaa7b23e,0x37e33b77,
0xb9edbbea,0xbbe2ba4f,0xb95fb0b2,0x317938ec,0x3564b3c6,0xb984bb99,0xbb88bbc3,0xb9cbb505,0x3bfe3a6d,0x3303b444,0xaa48b8c4,0xbbcebbb6,
0x36d73add,0x3b77393a,0x3b3b381d,0xb5c2ba0f,0xb78bae46,0x367c393a,0x3b0e3bf6,0x3b503a0f,0xbba8ba2f,0xb1792fd6,0x34a53913,0x3be23bf1,
0xbb0ebbf6,0xb984b732,0xb78bae46,0x39cb3b25,0xb4a5b913,0xbbcebaf6,0xbba8ba2f,0x330337e3,0x3bc33bfe,0x3a4f39cb,0x33c62a48,0xb8ecb984,
0x3a6d3b3b,0x3b253ac2,0x38c436d7,0xb732b848,0x381d395f,0x3bb63b77,0x3add39ed,0xb444b5c2,0x30b23564,0x3bfa3be2,0x3bea3b88,0xacb5b179,
0x3c003c00,0xb8ecb984,0,0x3a4f39cb,0x3c003c00,0xb732b848,0,0x3b253ac2,0x3c003c00,0xb444b5c2,0,0x3bb63b77,
0x3c003c00,0xacb5b179,0,0x3bfa3be2,0xb3c6aa48,0x3b503a0f,0xbbc3bbfe,0x367c393a,0xb8c4b6d7,0x3be23bf1,0xba6dbb3b,0xb1792fd6,
0xbaddb9ed,0x39cb3b25,0xb81db95f,0xb984b732,0xbbeabb88,0x330337e3,0xb0b2b564,0xbbcebaf6,0xbb0ebbf6,0x317938ec,0x378b2e46,0xbbe2ba4f,
0xb4a5b913,0xb9cbb505,0x3ba83a2f,0xb984bb99,0x378b2e46,0xbbcebbb6,0x3b0e3bf6,0x3303b444,0x3ba83a2f,0xb5c2ba0f,0x34a53913,0x3b77393a,
0x395f30b2,0xbbfaba8a,0x39ed3bea,0x2cb5b89b,0x3b883bc3,0xafd6b9cb,0xb56433c6,0x3bf13984,0x2a4838c4,0x3b993848,0xbbfeba6d,0x35053ac2,
0xbb3bb81d,0x37e33b77,0xb6d7badd,0xbaf6b5c2,0x38723bd9,0x3505b848,0xbaa7b23e,0x3b993ac2,0xbaa7b23e,0x3af63b77,0xb872bbd9,0xb7e335c2,
0xb872bbd9,0xb93a3179,0x3aa7323e,0xba0fbbe2,0x3aa7323e,0xb8ecbbff,0x38723bd9,0x3a4f2648,0xbb88b3c6,0x3ac23af6,0xb564bbc3,0xb84837e3,
0x2a48ba6d,0xbb50acb5,0x3bfe38c4,0xb67cbbfa,0x3b3b3add,0x3179ba4f,0xb6d7381d,0x3be238ec,0xb9ed30b2,0x39cb3b99,0xb95fbbea,0xb9843505,
0xae46bba8,0xb9cb3732,0x3bf634a5,0xb984bb25,0x3a2f3b0e,0x3303baf6,0xb913378b,0x3bce37e3,0xbbf6b4a5,0x35c23bfa,0xae46bba8,0xbb772cb5,
0x3913b78b,0xba8aba4f,0x3a2f3b0e,0x389bb8ec,0x3bea3564,0xb7e3bb50,0xb0b23b88,0x3af6b67c,0xbbc32a48,0x393a3a8a,0xb3c6bbfe,0xba0f389b,
0x3a6db6d7,0xba4fb984,0x38c43b3b,0x38ecb9cb,0xb81d39ed,0x3b253848,0xbaddb95f,0xb7323ac2,0xb61f3b64,0x3bb6b5c2,0xbb64b61f,0x34443b77,
0x361fbb64,0xbbfa3179,0x3b64361f,0xacb5bbe2,0xb61f3b64,0x3bf12648,0xbb64b61f,0xafd63bff,0x361fbb64,0xbb99b303,0x3b64361f,0x3505bbce,
0xba6db6d7,0x26483b99,0x38c4bb3b,0xbbff3505,0x381d39ed,0x3848bbb6,0xbadd395f,0x3ac23444,0xb0b2bb88,0xbb50393a,0x3beab564,0xb67cba0f,
0xb3c63bfe,0x3be2afd6,0xbbc3aa48,0xb1793bf1,0x3a2fbb0e,0xbbce3444,0x3913378b,0x3303bbb6,0xbbf634a5,0x35c2393a,0x2e46bba8,0xbb773a0f,
0x3913378b,0x389bbbf1,0xba2f3b0e,0x3a8a2fd6,0x2e46bba8,0xbbff3732,0x3bf6b4a5,0x2648bb25,0x36d7381d,0x3732bbce,0xbb3b3add,0x3b25b303,
0x395fbbea,0xbbb6367c,0x39ed30b2,0x3444bb50,0xbb8833c6,0xacb53a8a,0x3564bbc3,0xbbfa389b,0x2a483a6d,0x3bf1b9cb,0xbbfe38c4,0x2fd63984,
0xbbd93aa7,0x3a0fb179,0xb23eb872,0xb93a3be2,0x323e3872,0x3a4fbbff,0xbbd93aa7,0x38ec2648,0x3bd9baa7,0xb732b303,0x323e3872,0x3b25bbce,
0xb23eb872,0xbbb63b50,0x3bd9baa7,0xb444b67c,0x2a48b8c4,0xba8a3bf1,0x3bfeba6d,0xb89b2fd6,0xbb3b381d,0x26483732,0x36d7badd,0xbbff3b25,
0xb9ed3bea,0x3ac2b7e3,0xb95f30b2,0xb8483af6,0x356433c6,0x3b50bbfa,0xbb883bc3,0x367c2cb5,0x3ba8ba2f,0xb5c22cb5,0xb4a53913,0x3b77bbfa,
0x3b0ebbf6,0xba8a38ec,0x378bae46,0x389bba4f,0x34a5b913,0xbbff3b99,0x3ba8ba2f,0x2648b505,0xb78b2e46,0xbac23bb6,0x3b0ebbf6,0xb8483444,
0xb81d395f,0x3bf1bbff,0xbadd39ed,0x2fd6a648,0xb0b23564,0x3b99bbce,0xbbea3b88,0x3505b303,0x33c6aa48,0x3af6bb50,0xbbc33bfe,0x37e3b67c,
0x38c4b6d7,0x3a0fba8a,0xba6d3b3b,0x393ab89b,0xb9a839a8,0xafd62648,0x39a8b9a8,0xbbf13bff,0xb9a839a8,0xb5053303,0x39a8b9a8,0xbb993bce,
0xb9a839a8,0xb7e3367c,0x39a8b9a8,0xbaf63b50,0xb9a839a8,0xb93a389b,0x39a8b9a8,0xba0f3a8a,0x3addb9ed,0xbb773bfa,0x381db95f,0x35c2acb5,
0x3beabb88,0xb89b3a4f,0x30b2b564,0x3a8ab8ec,0x3bc3bbfe,0xa6483505,0xb3c62a48,0x3bffbb99,0x3a6dbb3b,0x3848b444,0xb8c436d7,0x3ac2bbb6,
0x34a5b913,0x389bafd6,0xbba83a2f,0x3a8abbf1,0xb78b2e46,0x3bffbb25,0xbb0e3bf6,0xa648b732,0xbba83a2f,0x3848baf6,0xb4a53913,0xbac237e3,
0xbb0e3bf6,0xb67cacb5,0x378bae46,0xbb503bfa,0xbbfe3a6d,0x393abbe2,0xaa4838c4,0xba0f3179,0xb6d73add,0xb8eca648,0x3b3bb81d,0xba4f3bff,
0x395fb0b2,0xbb253bce,0x39edbbea,0x37323303,0x3b88bbc3,0x3444367c,0xb564b3c6,0x3bb6bb50,0x323e3872,0xbb253303,0x3bd9baa7,0xb7323bce,
0x3bd9baa7,0xb4443b50,0xb23eb872,0x3bb6b67c,0xb23eb872,0x3bfab89b,0xbbd93aa7,0x2cb5ba8a,0xbbd93aa7,0xafd6b984,0x323e3872,0xbbf139cb,
0x3b3bbadd,0xb3033bb6,0xb6d7b81d,0x3bceb444,0xb9edb0b2,0x3b77ba0f,0xb95f3bea,0xb5c2b93a,0xb5643bc3,0xba8aafd6,0x3b88b3c6,0xb89b3bf1,
0x3bfeb8c4,0xa6483b25,0xaa48ba6d,0x3bffb732,0xb913b78b,0x3bffb505,0xba2f3b0e,0xa648bb99,0xae463ba8,0xbac2b444,0x3bf6b4a5,0xb8483bb6,
0x3a2fbb0e,0x367c3a0f,0xb913b78b,0x3b50b93a,0xbbf634a5,0x3179bbf1,0xae463ba8,0xbbe22fd6,0xb8c43b3b,0xb444bb77,0x3a6d36d7,0xbbb635c2,
0x3addb95f,0x2cb53be2,0xb81db9ed,0x3bfab179,0xbbea3564,0x2fd6bbff,0x30b23b88,0xbbf1a648,0x3bc32a48,0xb5053bce,0x33c6bbfe,0x3b993303,
0x3b64361f,0xbaf6367c,0x361fbb64,0x37e33b50,0xbb64b61f,0x3a0fb89b,0xb61f3b64,0xb93aba8a,0x3b64361f,0xb8ec39cb,0x361fbb64,0x3a4f3984,
0xbb64b61f,0x3732bac2,0xb61f3b64,0xbb25b848,0x30b2bb88,0x39843b25,0xbbeab564,0x39cbb732,0x33c63bfe,0xbbceb7e3,0x3bc3aa48,0xb3033af6,
0xb8c4bb3b,0x3b77acb5,0xba6d36d7,0xb5c2bbfa,0x3add395f,0xb89b38ec,0x381db9ed,0x3a8a3a4f,0xbbf6b4a5,0x3848b7e3,0x2e463ba8,0xbac2baf6,
0x3913b78b,0x367c3bfa,0xba2fbb0e,0x3b502cb5,0x2e463ba8,0xbbe2b8ec,0x3bf634a5,0xb1793a4f,0xba2fbb0e,0x3984b505,0xb913378b,0xb9cbbb99,
0x35643bc3,0xbb99bac2,0x3b8833c6,0xb5053848,0xbbfeb8c4,0x37e3b5c2,0xaa483a6d,0xbaf6bb77,0x36d7b81d,0x3a0f3be2,0xbb3bbadd,0x393ab179,
0x395f3bea,0xba4fa648,0x39edb0b2,0x38ec3bff,0x3aa7323e,0xacb5389b,0xb872bbd9,0x3bfa3a8a,0x38723bd9,0xbbf1b984,0x3aa7323e,0x2fd639cb,
0xbaa7b23e,0xb505bac2,0x38723bd9,0xbb99b848,0xb872bbd9,0x3af635c2,0xbaa7b23e,0xb7e3bb77,0xb9edbbea,0x3be23a4f,0xb95fb0b2,0xb179b8ec,
0x3564b3c6,0x39843b99,0xbb88bbc3,0x39cb3505,0x3bfe3a6d,0xb3033444,0xaa48b8c4,0x3bce3bb6,0x36d73add,0xbb77b93a,0x3b3b381d,0x35c23a0f,
0xb78bae46,0xb67cb93a,0x3b0e3bf6,0xbb50ba0f,0xbba8ba2f,0x3179afd6,0x34a53913,0xbbe2bbf1,0xbb0ebbf6,0x39843732,0xb78bae46,0xb9cbbb25,
0xb4a5b913,0x3bce3af6,0xbba8ba2f,0xb303b7e3,0x3bc33bfe,0xba4fb9cb,0x33c62a48,0x38ec3984,0x3a6d3b3b,0xbb25bac2,0x38c436d7,0x37323848,
0x381d395f,0xbbb6bb77,0x3add39ed,0x344435c2,0x30b23564,0xbbfabbe2,0x3bea3b88,0x2cb53179,0x3c003c00,0xafd6a648,0,0xbbf1bbff,
0x3c003c00,0xb505b303,0,0xbb99bbce,0x3c003c00,0xb7e3b67c,0,0xbaf6bb50,0x3c003c00,0xb93ab89b,0,0xba0fba8a,
0xbbc3bbfe,0x35c22cb5,0x33c62a48,0x3b773bfa,0xba6dbb3b,0x3a8a38ec,0x38c436d7,0x389b3a4f,0xb81db95f,0x3bff3b99,0x3add39ed,0x26483505,
0xb0b2b564,0x3ac23bb6,0x3bea3b88,0xb848b444,0x3b0e3bf6,0xb89bafd6,0xb78bae46,0xba8abbf1,0x34a53913,0xbbffbb25,0xbba8ba2f,0x2648b732,
0xb78bae46,0xb848baf6,0xbb0ebbf6,0x3ac237e3,0xbba8ba2f,0x367cacb5,0xb4a5b913,0x3b503bfa,0xb9edbbea,0x3a0f3179,0x395f30b2,0x393a3be2,
0x3564b3c6,0x3a4f3bff,0x3b883bc3,0xb8ec2648,0x3bfe3a6d,0xb7323303,0x2a4838c4,0xbb25bbce,0x36d73add,0xbbb6bb50,0xbb3bb81d,0x3444b67c,
0x38723bd9,0xbb25b303,0xbaa7b23e,0xb732bbce,0xbaa7b23e,0xb444bb50,0xb872bbd9,0x3bb6367c,0xb872bbd9,0x3bfa389b,0x3aa7323e,0x2cb53a8a,
0x3aa7323e,0xafd63984,0x38723bd9,0xbbf1b9cb,0xb564bbc3,0x3bce3444,0x3b8833c6,0x33033bb6,0x3bfe38c4,0xb5c2393a,0xaa483a6d,0xbb77ba0f,
0xb6d7381d,0xb89bbbf1,0xbb3bbadd,0x3a8aafd6,0xb95fbbea,0x3bff3732,0x39edb0b2,0x26483b25,0x2e463ba8,0xbbffb505,0xbbf6b4a5,0x2648bb99,
0xba2fbb0e,0x3ac2b444,0x3913b78b,0x38483bb6,0x3bf634a5,0xb67c3a0f,0x2e463ba8,0xbb50b93a,0xb913378b,0xb179bbf1,0xba2fbb0e,0x3be22fd6,
0x30b2bb88,0x3bb635c2,0x3bea3564,0xb4443b77,0x33c63bfe,0xbbfab179,0xbbc32a48,0x2cb5bbe2,0xb8c4bb3b,0x3bf1a648,0x3a6db6d7,0x2fd63bff,
0x3add395f,0xbb993303,0xb81d39ed,0xb505bbce,0xb61f3b64,0xbaf6b67c,0xbb64b61f,0x37e3bb50,0x361fbb64,0x3a0f389b,0x3b64361f,0xb93a3a8a,
0xb61f3b64,0xb8ecb9cb,0xbb64b61f,0x3a4fb984,0x361fbb64,0x37323ac2,0x3b64361f,0xbb253848,0x38c4bb3b,0x39cb3732,0x3a6d36d7,0xb9843b25,
0xbadd395f,0xb303baf6,0xb81db9ed,0x3bceb7e3,0x3beab564,0xb5c23bfa,0x30b23b88,0xbb77acb5,0xbbc3aa48,0x3a8aba4f,0x33c6bbfe,0x389b38ec,
0xba2f3b0e,0xb848b7e3,0xb913b78b,0x3ac2baf6,0x3bf6b4a5,0xb67c3bfa,0xae463ba8,0xbb502cb5,0xb913b78b,0x3be2b8ec,0x3a2fbb0e,0x31793a4f,
0xae463ba8,0xb984b505,0xbbf634a5,0x39cbbb99,0x3b3bbadd,0x35053848,0x36d7381d,0xbb993ac2,0xb9edb0b2,0x3af6bb77,0x395fbbea,0x37e335c2,
0xb5643bc3,0xb93ab179,0xbb8833c6,0x3a0fbbe2,0x3bfeb8c4,0xb8ec3bff,0x2a483a6d,0xba4f2648,0xbbd93aa7,0xacb5b89b,0xb23eb872,0x3bfaba8a,
0x323e3872,0xbbf13984,0xbbd93aa7,0x2fd6b9cb,0x3bd9baa7,0xb5053ac2,0x323e3872,0xbb993848,0xb23eb872,0x3af6b5c2,0x3bd9baa7,0xb7e33b77,
0x3bfeba6d,0xb17938ec,0xaa4838c4,0xbbe23a4f,0x36d7badd,0x39cbb505,0x3b3bb81d,0xb9843b99,0xb95f30b2,0x3bcebbb6,0x39edbbea,0x33033444,
0xbb883bc3,0x35c2ba0f,0xb564b3c6,0x3b77b93a,0xbba83a2f,0x367cb93a,0x34a5b913,0x3b50ba0f,0xbb0e3bf6,0xb179afd6,0xb78b2e46,0x3be2bbf1,
0xb4a53913,0xb9843732,0xbba83a2f,0x39cbbb25,0x378bae46,0xbbce3af6,0xbb0e3bf6,0x3303b7e3,0x3addb9ed,0xb8ec3984,0xb81d395f,0xba4f39cb,
0x3beabb88,0xb7323848,0xb0b23564,0xbb253ac2,0x3bc3bbfe,0xb44435c2,0x33c6aa48,0xbbb63b77,0x3a6dbb3b,0xacb53179,0x38c4b6d7,0xbbfa3be2,
0xb9a839a8,0x3a4fb9cb,0x39a8b9a8,0x38ecb984,0xb9a839a8,0x3b25bac2,0x39a8b9a8,0x3732b848,0xb9a839a8,0x3bb6bb77,0x39a8b9a8,0x3444b5c2,
0xb9a839a8,0x3bfabbe2,0x39a8b9a8,0x2cb5b179,0x381db95f,0xbb503a0f,0xbadd39ed,0xb67c393a,0x30b2b564,0xbbe23bf1,0xbbea3b88,0x31792fd6,
0xb3c62a48,0xb9cb3b25,0xbbc33bfe,0x3984b732,0xb8c436d7,0xb30337e3,0xba6d3b3b,0x3bcebaf6,0xb4a53913,0x3be2ba4f,0x3ba8ba2f,0x3179b8ec,
0x378bae46,0x3984bb99,0x3b0ebbf6,0xb9cb3505,0x3ba8ba2f,0xb303b444,0x34a5b913,0xbbce3bb6,0x3b0ebbf6,0xbb77393a,0xb78b2e46,0xb5c23a0f,
0x2a48b8c4,0xbbfa3a8a,0xbbfe3a6d,0x2cb5389b,0xbb3b381d,0xafd639cb,0xb6d73add,0x3bf1b984,0xb9ed3bea,0x3b99b848,0x395fb0b2,0x3505bac2,
0x356433c6,0x37e3bb77,0x3b88bbc3,0xbaf635c2,0x323e3872,0x3b99bac2,0x3bd9baa7,0xb505b848,0x3bd9baa7,0xb7e3b5c2,0xb23eb872,0xbaf63b77,
0xb23eb872,0xba0f3be2,0xbbd93aa7,0x393a3179,0xbbd93aa7,0x3a4fa648,0x323e3872,0x38ecbbff,0xb6d7b81d,0xbac23af6,0xbb3b3add,0x384837e3,
0xb95f3bea,0x3b50acb5,0x39ed30b2,0x367cbbfa,0x3b88b3c6,0xb179ba4f,0x3564bbc3,0xbbe238ec,0xaa48ba6d,0xb9cb3b99,0xbbfe38c4,0x39843505,
0x3913378b,0x3984bb25,0x3a2fbb0e,0xb9cbb732,0x2e46bba8,0xbbce37e3,0xbbf634a5,0x33033af6,0xba2f3b0e,0x3b772cb5,0x3913378b,0x35c2bbfa,
0x3bf6b4a5,0xb89bb8ec,0x2e46bba8,0xba8a3a4f,0xba6db6d7,0xb7e33b50,0xb8c43b3b,0x3af6367c,0x381d39ed,0x393aba8a,0x3addb95f,0xba0fb89b,
0xb0b2bb88,0xba4f3984,0xbbea3564,0x38ec39cb,0xb3c63bfe,0x3b25b848,0x3bc32a48,0xb732bac2,0x3b64361f,0x3444bb77,0x361fbb64,0xbbb6b5c2,
0xbb64b61f,0xacb53be2,0xb61f3b64,0x3bfa3179,0x3b64361f,0xafd6bbff,0x361fbb64,0xbbf12648,0xbb64b61f,0x35053bce,0xb61f3b64,0x3b99b303,
0xbbeab564,0xa6483b99,0xb0b23b88,0x3bff3505,0x3bc3aa48,0xb848bbb6,0xb3c6bbfe,0xbac23444,0xba6d36d7,0x3b50393a,0x38c43b3b,0x367cba0f,
0x381db9ed,0xbbe2afd6,0xbaddb95f,0x31793bf1,0x3bf634a5,0xb303bbb6,0xae46bba8,0xbbceb444,0xb913378b,0x3b773a0f,0x3a2f3b0e,0x35c2b93a,
0xae46bba8,0xba8a2fd6,0xbbf6b4a5,0x389b3bf1,0x3a2f3b0e,0xa648bb25,0x3913b78b,0xbbffb732,0xbb88b3c6,0x37323bce,0x35643bc3,0x3b253303,
0x2a48ba6d,0xbbb6b67c,0xbbfeb8c4,0x34443b50,0x3b3b3add,0xacb5ba8a,0x36d7b81d,0xbbfab89b,0xb9ed30b2,0x3bf139cb,0x395f3bea,0x2fd6b984,
0x3aa7323e,0xb93abbe2,0xb872bbd9,0xba0fb179,0x38723bd9,0x38eca648,0x3aa7323e,0xba4fbbff,0xbaa7b23e,0x3b253bce,0x38723bd9,0x3732b303,
0xb872bbd9,0xb444367c,0xbaa7b23e,0x3bb63b50,0xb95fb0b2,0x3a8a3bf1,0x39ed3bea,0x389b2fd6,0xbb88bbc3,0xa6483732,0xb56433c6,0x3bff3b25,
0xaa48b8c4,0xbac2b7e3,0xbbfeba6d,0x38483af6,0x3b3b381d,0xbb50bbfa,0xb6d7badd,0xb67c2cb5,0x378b2e46,0xbb77bbfa,0xbb0ebbf6,0xb5c2acb5,
0x3ba83a2f,0xb89bba4f,0xb4a5b913,0xba8ab8ec,0x3b0e3bf6,0xa648b505,0x378b2e46,0xbbffbb99,0x34a53913,0x38483444,0x3ba83a2f,0xbac2bbb6,
0xb3c6aa48,0x3bf13bff,0x3bc33bfe,0x2fd62648,0xb8c4b6d7,0x3b993bce,0x3a6d3b3b,0x35053303,0xbaddb9ed,0x3af63b50,0x381d395f,0x37e3367c,
0xbbeabb88,0x3a0f3a8a,0x30b23564,0x393a389b,0x3c003c00,0x2fd62648,0,0x3bf13bff,0x3c003c00,0x35053303,0,0x3b993bce,
0x3c003c00,0x37e3367c,0,0x3af63b50,0x3c003c00,0x393a389b,0,0x3a0f3a8a,0xbbc3bbfe,0xb5c2acb5,0x33c62a48,0xbb77bbfa,
0xba6dbb3b,0xba8ab8ec,0x38c436d7,0xb89bba4f,0xb81db95f,0xbbffbb99,0x3add39ed,0xa648b505,0xb0b2b564,0xbac2bbb6,0x3bea3b88,0x38483444,
0x3b0e3bf6,0x389b2fd6,0xb78bae46,0x3a8a3bf1,0x34a53913,0x3bff3b25,0xbba8ba2f,0xa6483732,0xb78bae46,0x38483af6,0xbb0ebbf6,0xbac2b7e3,
0xbba8ba2f,0xb67c2cb5,0xb4a5b913,0xbb50bbfa,0xb9edbbea,0xba0fb179,0x395f30b2,0xb93abbe2,0x3564b3c6,0xba4fbbff,0x3b883bc3,0x38eca648,
0x3bfe3a6d,0x3732b303,0x2a4838c4,0x3b253bce,0x36d73add,0x3bb63b50,0xbb3bb81d,0xb444367c,0x38723bd9,0x3b253303,0xbaa7b23e,0x37323bce,
0xbaa7b23e,0x34443b50,0xb872bbd9,0xbbb6b67c,0xb872bbd9,0xbbfab89b,0x3aa7323e,0xacb5ba8a,0x3aa7323e,0x2fd6b984,0x38723bd9,0x3bf139cb,
0xb564bbc3,0xbbceb444,0x3b8833c6,0xb303bbb6,0x3bfe38c4,0x35c2b93a,0xaa483a6d,0x3b773a0f,0xb6d7381d,0x389b3bf1,0xbb3bbadd,0xba8a2fd6,
0xb95fbbea,0xbbffb732,0x39edb0b2,0xa648bb25,0x2e463ba8,0x3bff3505,0xbbf6b4a5,0xa6483b99,0xba2fbb0e,0xbac23444,0x3913b78b,0xb848bbb6,
0x3bf634a5,0x367cba0f,0x2e463ba8,0x3b50393a,0xb913378b,0x31793bf1,0xba2fbb0e,0xbbe2afd6,0x30b2bb88,0xbbb6b5c2,0x3bea3564,0x3444bb77,
0x33c63bfe,0x3bfa3179,0xbbc32a48,0xacb53be2,0xb8c4bb3b,0xbbf12648,0x3a6db6d7,0xafd6bbff,0x3add395f,0x3b99b303,0xb81d39ed,0x35053bce,
0xb61f3b64,0x3af6367c,0xbb64b61f,0xb7e33b50,0x361fbb64,0xba0fb89b,0x3b64361f,0x393aba8a,0xb61f3b64,0x38ec39cb,0xbb64b61f,0xba4f3984,
0x361fbb64,0xb732bac2,0x3b64361f,0x3b25b848,0x38c4bb3b,0xb9cbb732,0x3a6d36d7,0x3984bb25,0xbadd395f,0x33033af6,0xb81db9ed,0xbbce37e3,
0x3beab564,0x35c2bbfa,0x30b23b88,0x3b772cb5,0xbbc3aa48,0xba8a3a4f,0x33c6bbfe,0xb89bb8ec,0xba2f3b0e,0x384837e3,0xb913b78b,0xbac23af6,
0x3bf6b4a5,0x367cbbfa,0xae463ba8,0x3b50acb5,0xb913b78b,0xbbe238ec,0x3a2fbb0e,0xb179ba4f,0xae463ba8,0x39843505,0xbbf634a5,0xb9cb3b99,
0x3b3bbadd,0xb505b848,0x36d7381d,0x3b99bac2,0xb9edb0b2,0xbaf63b77,0x395fbbea,0xb7e3b5c2,0xb5643bc3,0x393a3179,0xbb8833c6,0xba0f3be2,
0x3bfeb8c4,0x38ecbbff,0x2a483a6d,0x3a4fa648,0xbbd93aa7,0x2cb5389b,0xb23eb872,0xbbfa3a8a,0x323e3872,0x3bf1b984,0xbbd93aa7,0xafd639cb,
0x3bd9baa7,0x3505bac2,0x323e3872,0x3b99b848,0xb23eb872,0xbaf635c2,0x3bd9baa7,0x37e3bb77,0x3bfeba6d,0x3179b8ec,0xaa4838c4,0x3be2ba4f,
0x36d7badd,0xb9cb3505,0x3b3bb81d,0x3984bb99,0xb95f30b2,0xbbce3bb6,0x39edbbea,0xb303b444,0xbb883bc3,0xb5c23a0f,0xb564b3c6,0xbb77393a,
0xbba83a2f,0xb67c393a,0x34a5b913,0xbb503a0f,0xbb0e3bf6,0x31792fd6,0xb78b2e46,0xbbe23bf1,0xb4a53913,0x3984b732,0xbba83a2f,0xb9cb3b25,
0x378bae46,0x3bcebaf6,0xbb0e3bf6,0xb30337e3,0x3addb9ed,0x38ecb984,0xb81d395f,0x3a4fb9cb,0x3beabb88,0x3732b848,0xb0b23564,0x3b25bac2,
0x3bc3bbfe,0x3444b5c2,0x33c6aa48,0x3bb6bb77,0x3a6dbb3b,0x2cb5b179,0x38c4b6d7,0x3bfabbe2,0xb9a839a8,0xba4f39cb,0x39a8b9a8,0xb8ec3984,
0xb9a839a8,0xbb253ac2,0x39a8b9a8,0xb7323848,0xb9a839a8,0xbbb63b77,0x39a8b9a8,0xb44435c2,0xb9a839a8,0xbbfa3be2,0x39a8b9a8,0xacb53179,
0x381db95f,0x3b50ba0f,0xbadd39ed,0x367cb93a,0x30b2b564,0x3be2bbf1,0xbbea3b88,0xb179afd6,0xb3c62a48,0x39cbbb25,0xbbc33bfe,0xb9843732,
0xb8c436d7,0x3303b7e3,0xba6d3b3b,0xbbce3af6,0xb4a53913,0xbbe23a4f,0x3ba8ba2f,0xb17938ec,0x378bae46,0xb9843b99,0x3b0ebbf6,0x39cbb505,
0x3ba8ba2f,0x33033444,0x34a5b913,0x3bcebbb6,0x3b0ebbf6,0x3b77b93a,0xb78b2e46,0x35c2ba0f,0x2a48b8c4,0x3bfaba8a,0xbbfe3a6d,0xacb5b89b,
0xbb3b381d,0x2fd6b9cb,0xb6d73add,0xbbf13984,0xb9ed3bea,0xbb993848,0x395fb0b2,0xb5053ac2,0x356433c6,0xb7e33b77,0x3b88bbc3,0x3af6b5c2,
0x323e3872,0xbb993ac2,0x3bd9baa7,0x35053848,0x3bd9baa7,0x37e335c2,0xb23eb872,0x3af6bb77,0xb23eb872,0x3a0fbbe2,0xbbd93aa7,0xb93ab179,
0xbbd93aa7,0xba4f2648,0x323e3872,0xb8ec3bff,0xb6d7b81d,0x3ac2baf6,0xbb3b3add,0xb848b7e3,0xb95f3bea,0xbb502cb5,0x39ed30b2,0xb67c3bfa,
0x3b88b3c6,0x31793a4f,0x3564bbc3,0x3be2b8ec,0xaa48ba6d,0x39cbbb99,0xbbfe38c4,0xb984b505,0x3913378b,0xb9843b25,0x3a2fbb0e,0x39cb3732,
0x2e46bba8,0x3bceb7e3,0xbbf634a5,0xb303baf6,0xba2f3b0e,0xbb77acb5,0x3913378b,0xb5c23bfa,0x3bf6b4a5,0x389b38ec,0x2e46bba8,0x3a8aba4f,
0xba6db6d7,0x37e3bb50,0xb8c43b3b,0xbaf6b67c,0x381d39ed,0xb93a3a8a,0x3addb95f,0x3a0f389b,0xb0b2bb88,0x3a4fb984,0xbbea3564,0xb8ecb9cb,
0xb3c63bfe,0xbb253848,0x3bc32a48,0x37323ac2,0x3b64361f,0xb4443b77,0x361fbb64,0x3bb635c2,0xbb64b61f,0x2cb5bbe2,0xb61f3b64,0xbbfab179,
0x3b64361f,0x2fd63bff,0x361fbb64,0x3bf1a648,0xbb64b61f,0xb505bbce,0xb61f3b64,0xbb993303,0xbbeab564,0x2648bb99,0xb0b23b88,0xbbffb505,
0x3bc3aa48,0x38483bb6,0xb3c6bbfe,0x3ac2b444,0xba6d36d7,0xbb50b93a,0x38c43b3b,0xb67c3a0f,0x381db9ed,0x3be22fd6,0xbaddb95f,0xb179bbf1,
0x3bf634a5,0x33033bb6,0xae46bba8,0x3bce3444,0xb913378b,0xbb77ba0f,0x3a2f3b0e,0xb5c2393a,0xae46bba8,0x3a8aafd6,0xbbf6b4a5,0xb89bbbf1,
0x3a2f3b0e,0x26483b25,0x3913b78b,0x3bff3732,0xbb88b3c6,0xb732bbce,0x35643bc3,0xbb25b303,0x2a48ba6d,0x3bb6367c,0xbbfeb8c4,0xb444bb50,
0x3b3b3add,0x2cb53a8a,0x36d7b81d,0x3bfa389b,0xb9ed30b2,0xbbf1b9cb,0x395f3bea,0xafd63984,0x3aa7323e,0x393a3be2,0xb872bbd9,0x3a0f3179,
0x38723bd9,0xb8ec2648,0x3aa7323e,0x3a4f3bff,0xbaa7b23e,0xbb25bbce,0x38723bd9,0xb7323303,0xb872bbd9,0x3444b67c,0xbaa7b23e,0xbbb6bb50,
0xb95fb0b2,0xba8abbf1,0x39ed3bea,0xb89bafd6,0xbb88bbc3,0x2648b732,0xb56433c6,0xbbffbb25,0xaa48b8c4,0x3ac237e3,0xbbfeba6d,0xb848baf6,
0x3b3b381d,0x3b503bfa,0xb6d7badd,0x367cacb5,0x378b2e46,0x3b773bfa,0xbb0ebbf6,0x35c22cb5,0x3ba83a2f,0x389b3a4f,0xb4a5b913,0x3a8a38ec,
0x3b0e3bf6,0x26483505,0x378b2e46,0x3bff3b99,0x34a53913,0xb848b444,0x3ba83a2f,0x3ac23bb6,0xb3c6aa48,0xbbf1bbff,0x3bc33bfe,0xafd6a648,
0xb8c4b6d7,0xbb99bbce,0x3a6d3b3b,0xb505b303,0xbaddb9ed,0xbaf6bb50,0x381d395f,0xb7e3b67c,0xbbeabb88,0xba0fba8a,0x30b23564,0xb93ab89b,
0x3c003c00,0xba4fb9cb,0,0xb8ecb984,0x3c003c00,0xbb25bac2,0,0xb732b848,0x3c003c00,0xbbb6bb77,0,0xb444b5c2,
0x3c003c00,0xbbfabbe2,0,0xacb5b179,0x33c62a48,0x367c393a,0x3bc33bfe,0xbb50ba0f,0x38c436d7,0xb1792fd6,0x3a6d3b3b,0xbbe2bbf1,
0x3add39ed,0xb984b732,0x381d395f,0xb9cbbb25,0x3bea3b88,0xbbcebaf6,0x30b23564,0xb303b7e3,0xbb0ebbf6,0x3be23a4f,0x378b2e46,0x317938ec,
0xb4a5b913,0x39843b99,0x3ba83a2f,0xb9cbb505,0x378b2e46,0xb3033444,0x3b0e3bf6,0xbbcebbb6,0x3ba83a2f,0xbb77b93a,0x34a53913,0xb5c2ba0f,
0xb95fb0b2,0x2cb5b89b,0xb9edbbea,0x3bfa3a8a,0xbb88bbc3,0x3bf13984,0x3564b3c6,0x2fd639cb,0xaa48b8c4,0x35053ac2,0x3bfe3a6d,0xbb99b848,
0x3b3b381d,0xbaf6b5c2,0x36d73add,0xb7e3bb77,0x38723bd9,0xbb99bac2,0xbaa7b23e,0x3505b848,0xbaa7b23e,0x37e3b5c2,0xb872bbd9,0x3af63b77,
0xb872bbd9,0x3a0f3be2,0x3aa7323e,0xb93a3179,0x3aa7323e,0xba4fa648,0x38723bd9,0xb8ecbbff,0x3b8833c6,0xb84837e3,0x35643bc3,0xbac2baf6,
0xaa483a6d,0xb67cbbfa,0xbbfeb8c4,0x3b502cb5,0xbb3bbadd,0x3be238ec,0x36d7b81d,0xb1793a4f,0x39edb0b2,0xb9843505,0x395f3bea,0xb9cbbb99,
0xae46bba8,0x39843b25,0x3bf634a5,0xb9cb3732,0x3a2f3b0e,0xbbceb7e3,0xb913378b,0x3303baf6,0xbbf6b4a5,0x3b77acb5,0xae46bba8,0x35c23bfa,
0x3913b78b,0xb89b38ec,0x3a2f3b0e,0xba8aba4f,0xbbeab564,0x3af6b67c,0x30b2bb88,0x37e33b50,0x3bc3aa48,0xba0f389b,0x33c63bfe,0xb93aba8a,
0xba6d36d7,0x38ecb9cb,0xb8c4bb3b,0x3a4f3984,0x381db9ed,0xb7323ac2,0x3add395f,0xbb25b848,0xb61f3b64,0xb444bb77,0xbb64b61f,0x3bb6b5c2,
0x361fbb64,0x2cb53be2,0x3b64361f,0xbbfa3179,0xb61f3b64,0x2fd6bbff,0xbb64b61f,0x3bf12648,0x361fbb64,0xb5053bce,0x3b64361f,0xbb99b303,
0x3a6d36d7,0xbbff3505,0xb8c43b3b,0xa648bb99,0xb81db9ed,0x3ac23444,0x3addb95f,0xb8483bb6,0x30b23b88,0xb67cba0f,0xbbea3564,0x3b50b93a,
0x33c6bbfe,0xb1793bf1,0x3bc32a48,0xbbe22fd6,0x3a2fbb0e,0xb3033bb6,0x3913378b,0xbbce3444,0xbbf634a5,0x3b77ba0f,0x2e46bba8,0x35c2393a,
0x3913378b,0xba8aafd6,0xba2f3b0e,0x389bbbf1,0x2e46bba8,0xa6483b25,0x3bf6b4a5,0xbbff3732,0xb6d7b81d,0x3b25b303,0x3b3bbadd,0xb7323bce,
0xb95f3bea,0x3444bb50,0xb9edb0b2,0x3bb6b67c,0x3b88b3c6,0xbbfa389b,0xb5643bc3,0x2cb5ba8a,0xaa48ba6d,0x2fd63984,0x3bfeb8c4,0xbbf139cb,
0xbbd93aa7,0x393abbe2,0xb23eb872,0x3a0fb179,0x323e3872,0xb8eca648,0xbbd93aa7,0x3a4fbbff,0x3bd9baa7,0xbb253bce,0x323e3872,0xb732b303,
0xb23eb872,0x3444367c,0x3bd9baa7,0xbbb63b50,0xaa4838c4,0xb89b2fd6,0xbbfe3a6d,0x3a8abbf1,0x3b3bb81d,0xbbff3b25,0xb6d73add,0xa648b732,
0x39edbbea,0xb8483af6,0x395fb0b2,0xbac237e3,0xb564b3c6,0x367c2cb5,0x3b88bbc3,0xbb503bfa,0x3ba8ba2f,0xbb773bfa,0xb4a53913,0xb5c22cb5,
0x3b0ebbf6,0xb89b3a4f,0x378bae46,0xba8a38ec,0x34a5b913,0xa6483505,0x3ba8ba2f,0xbbff3b99,0xb78b2e46,0x3848b444,0x3b0ebbf6,0xbac23bb6,
0x381db95f,0x2fd6a648,0x3addb9ed,0xbbf13bff,0x30b2b564,0x3505b303,0x3beabb88,0xbb993bce,0xb3c62a48,0x37e3b67c,0x3bc3bbfe,0xbaf63b50,
0xb8c436d7,0x393ab89b,0x3a6dbb3b,0xba0f3a8a,0xb9a839a8,0x3bf1bbff,0x39a8b9a8,0xafd62648,0xb9a839a8,0x3b99bbce,0x39a8b9a8,0xb5053303,
0xb9a839a8,0x3af6bb50,0x39a8b9a8,0xb7e3367c,0xb9a839a8,0x3a0fba8a,0x39a8b9a8,0xb93a389b,0xbadd39ed,0x35c2acb5,0xb81d395f,0x3b77bbfa,
0xbbea3b88,0x3a8ab8ec,0xb0b23564,0x389bba4f,0xbbc33bfe,0x3bffbb99,0x33c6aa48,0x2648b505,0xba6d3b3b,0x3ac2bbb6,0x38c4b6d7,0xb8483444,
0x34a5b913,0xba8a3bf1,0xbba83a2f,0x389bafd6,0xb78b2e46,0x26483732,0xbb0e3bf6,0x3bffbb25,0xbba83a2f,0x3ac2b7e3,0xb4a53913,0x3848baf6,
0xbb0e3bf6,0x3b50bbfa,0x378bae46,0xb67cacb5,0x3bfeba6d,0xba0f3179,0x2a48b8c4,0xb93a3be2,0x36d7badd,0xba4f3bff,0xbb3b381d,0x38ec2648,
0xb95f30b2,0x37323303,0xb9ed3bea,0x3b25bbce,0xbb883bc3,0x3bb6bb50,0x356433c6,0xb444b67c,0x323e3872,0x3732bbce,0x3bd9baa7,0xbb253303,
0x3bd9baa7,0xbbb6367c,0xb23eb872,0xb4443b50,0xb23eb872,0xacb53a8a,0xbbd93aa7,0x3bfab89b,0xbbd93aa7,0x3bf1b9cb,0x323e3872,0xafd6b984,
0xbb3b3add,0x3bceb444,0x36d7381d,0x3303bbb6,0x39ed30b2,0xb5c2b93a,0x395fbbea,0xbb773a0f,0x3564bbc3,0xb89b3bf1,0xbb8833c6,0x3a8a2fd6,
0xbbfe38c4,0x3bffb732,0x2a483a6d,0x2648bb25,0xb913b78b,0x26483b99,0xba2f3b0e,0x3bffb505,0xae463ba8,0x3848bbb6,0x3bf6b4a5,0xbac2b444,
0x3a2fbb0e,0xbb50393a,0xb913b78b,0x367c3a0f,0xbbf634a5,0x3be2afd6,0xae463ba8,0x3179bbf1,0x38c4bb3b,0xbbb635c2,0xba6db6d7,0x34443b77,
0xbadd395f,0x3bfab179,0x381d39ed,0xacb5bbe2,0x3beab564,0xbbf1a648,0xb0b2bb88,0xafd63bff,0xbbc3aa48,0x3b993303,0xb3c63bfe,0x3505bbce,
0x3b64361f,0xb7e3bb50,0x361fbb64,0xbaf6367c,0xbb64b61f,0x393a3a8a,0xb61f3b64,0x3a0fb89b,0x3b64361f,0xba4fb984,0x361fbb64,0xb8ec39cb,
0xbb64b61f,0x3b253848,0xb61f3b64,0x3732bac2,0xb0b23b88,0x39cbb732,0x3bea3564,0xb984bb25,0xb3c6bbfe,0xb3033af6,0xbbc32a48,0x3bce37e3,
0x38c43b3b,0xb5c2bbfa,0x3a6db6d7,0xbb772cb5,0xbaddb95f,0x3a8a3a4f,0xb81d39ed,0x389bb8ec,0xbbf6b4a5,0x3ac23af6,0x2e463ba8,0x3848b7e3,
0x3913b78b,0xbb50acb5,0xba2fbb0e,0x367c3bfa,0x2e463ba8,0x3179ba4f,0x3bf634a5,0xbbe2b8ec,0xba2fbb0e,0x39cb3b99,0xb913378b,0x3984b505,
0xb564bbc3,0xb5053848,0xbb88b3c6,0x3b993ac2,0x3bfe38c4,0xbaf6bb77,0x2a48ba6d,0xb7e335c2,0xb6d7381d,0x393ab179,0x3b3b3add,0xba0fbbe2,
0xb95fbbea,0x38ec3bff,0xb9ed30b2,0x3a4f2648,0x3aa7323e,0xbbfaba8a,0xb872bbd9,0xacb5389b,0x38723bd9,0xafd6b9cb,0x3aa7323e,0xbbf1b984,
0xbaa7b23e,0x3b993848,0x38723bd9,0xb505bac2,0xb872bbd9,0x37e33b77,0xbaa7b23e,0x3af635c2,0x39ed3bea,0xb179b8ec,0x395f30b2,0xbbe2ba4f,
0xb56433c6,0x39cb3505,0x3b883bc3,0xb984bb99,0xbbfeba6d,0x3bce3bb6,0x2a4838c4,0x3303b444,0xb6d7badd,0x35c23a0f,0xbb3bb81d,0x3b77393a,
0xb78bae46,0x3b503a0f,0x3b0e3bf6,0xb67cb93a,0xbba8ba2f,0x3be23bf1,0x34a53913,0x3179afd6,0xbb0ebbf6,0x39cb3b25,0xb78bae46,0x39843732,
0xb4a5b913,0x330337e3,0xbba8ba2f,0x3bce3af6,0xbbc3bbfe,0x38ec3984,0xb3c6aa48,0x3a4f39cb,0xba6dbb3b,0x37323848,0xb8c4b6d7,0x3b253ac2,
0xb81db95f,0x344435c2,0xbaddb9ed,0x3bb63b77,0xb0b2b564,0x2cb53179,0xbbeabb88,0x3bfa3be2,0x3c003c00,0x3a4f39cb,0,0x38ec3984,
0x3c003c00,0x3b253ac2,0,0x37323848,0x3c003c00,0x3bb63b77,0,0x344435c2,0x3c003c00,0x3bfa3be2,0,0x2cb53179,
0x33c62a48,0xb67cb93a,0x3bc33bfe,0x3b503a0f,0x38c436d7,0x3179afd6,0x3a6d3b3b,0x3be23bf1,0x3add39ed,0x39843732,0x381d395f,0x39cb3b25,
0x3bea3b88,0x3bce3af6,0x30b23564,0x330337e3,0xbb0ebbf6,0xbbe2ba4f,0x378b2e46,0xb179b8ec,0xb4a5b913,0xb984bb99,0x3ba83a2f,0x39cb3505,
0x378b2e46,0x3303b444,0x3b0e3bf6,0x3bce3bb6,0x3ba83a2f,0x3b77393a,0x34a53913,0x35c23a0f,0xb95fb0b2,0xacb5389b,0xb9edbbea,0xbbfaba8a,
0xbb88bbc3,0xbbf1b984,0x3564b3c6,0xafd6b9cb,0xaa48b8c4,0xb505bac2,0x3bfe3a6d,0x3b993848,0x3b3b381d,0x3af635c2,0x36d73add,0x37e33b77,
0x38723bd9,0x3b993ac2,0xbaa7b23e,0xb5053848,0xbaa7b23e,0xb7e335c2,0xb872bbd9,0xbaf6bb77,0xb872bbd9,0xba0fbbe2,0x3aa7323e,0x393ab179,
0x3aa7323e,0x3a4f2648,0x38723bd9,0x38ec3bff,0x3b8833c6,0x3848b7e3,0x35643bc3,0x3ac23af6,0xaa483a6d,0x367c3bfa,0xbbfeb8c4,0xbb50acb5,
0xbb3bbadd,0xbbe2b8ec,0x36d7b81d,0x3179ba4f,0x39edb0b2,0x3984b505,0x395f3bea,0x39cb3b99,0xae46bba8,0xb984bb25,0x3bf634a5,0x39cbb732,
0x3a2f3b0e,0x3bce37e3,0xb913378b,0xb3033af6,0xbbf6b4a5,0xbb772cb5,0xae46bba8,0xb5c2bbfa,0x3913b78b,0x389bb8ec,0x3a2f3b0e,0x3a8a3a4f,
0xbbeab564,0xbaf6367c,0x30b2bb88,0xb7e3bb50,0x3bc3aa48,0x3a0fb89b,0x33c63bfe,0x393a3a8a,0xba6d36d7,0xb8ec39cb,0xb8c4bb3b,0xba4fb984,
0x381db9ed,0x3732bac2,0x3add395f,0x3b253848,0xb61f3b64,0x34443b77,0xbb64b61f,0xbbb635c2,0x361fbb64,0xacb5bbe2,0x3b64361f,0x3bfab179,
0xb61f3b64,0xafd63bff,0xbb64b61f,0xbbf1a648,0x361fbb64,0x3505bbce,0x3b64361f,0x3b993303,0x3a6d36d7,0x3bffb505,0xb8c43b3b,0x26483b99,
0xb81db9ed,0xbac2b444,0x3addb95f,0x3848bbb6,0x30b23b88,0x367c3a0f,0xbbea3564,0xbb50393a,0x33c6bbfe,0x3179bbf1,0x3bc32a48,0x3be2afd6,
0x3a2fbb0e,0x3303bbb6,0x3913378b,0x3bceb444,0xbbf634a5,0xbb773a0f,0x2e46bba8,0xb5c2b93a,0x3913378b,0x3a8a2fd6,0xba2f3b0e,0xb89b3bf1,
0x2e46bba8,0x2648bb25,0x3bf6b4a5,0x3bffb732,0xb6d7b81d,0xbb253303,0x3b3bbadd,0x3732bbce,0xb95f3bea,0xb4443b50,0xb9edb0b2,0xbbb6367c,
0x3b88b3c6,0x3bfab89b,0xb5643bc3,0xacb53a8a,0xaa48ba6d,0xafd6b984,0x3bfeb8c4,0x3bf1b9cb,0xbbd93aa7,0xb93a3be2,0xb23eb872,0xba0f3179,
0x323e3872,0x38ec2648,0xbbd93aa7,0xba4f3bff,0x3bd9baa7,0x3b25bbce,0x323e3872,0x37323303,0xb23eb872,0xb444b67c,0x3bd9baa7,0x3bb6bb50,
0xaa4838c4,0x389bafd6,0xbbfe3a6d,0xba8a3bf1,0x3b3bb81d,0x3bffbb25,0xb6d73add,0x26483732,0x39edbbea,0x3848baf6,0x395fb0b2,0x3ac2b7e3,
0xb564b3c6,0xb67cacb5,0x3b88bbc3,0x3b50bbfa,0x3ba8ba2f,0x3b77bbfa,0xb4a53913,0x35c2acb5,0x3b0ebbf6,0x389bba4f,0x378bae46,0x3a8ab8ec,
0x34a5b913,0x2648b505,0x3ba8ba2f,0x3bffbb99,0xb78b2e46,0xb8483444,0x3b0ebbf6,0x3ac2bbb6,0x381db95f,0xafd62648,0x3addb9ed,0x3bf1bbff,
0x30b2b564,0xb5053303,0x3beabb88,0x3b99bbce,0xb3c62a48,0xb7e3367c,0x3bc3bbfe,0x3af6bb50,0xb8c436d7,0xb93a389b,0x3a6dbb3b,0x3a0fba8a,
0xb9a839a8,0xbbf13bff,0x39a8b9a8,0x2fd6a648,0xb9a839a8,0xbb993bce,0x39a8b9a8,0x3505b303,0xb9a839a8,0xbaf63b50,0x39a8b9a8,0x37e3b67c,
0xb9a839a8,0xba0f3a8a,0x39a8b9a8,0x393ab89b,0xbadd39ed,0xb5c22cb5,0xb81d395f,0xbb773bfa,0xbbea3b88,0xba8a38ec,0xb0b23564,0xb89b3a4f,
0xbbc33bfe,0xbbff3b99,0x33c6aa48,0xa6483505,0xba6d3b3b,0xbac23bb6,0x38c4b6d7,0x3848b444,0x34a5b913,0x3a8abbf1,0xbba83a2f,0xb89b2fd6,
0xb78b2e46,0xa648b732,0xbb0e3bf6,0xbbff3b25,0xbba83a2f,0xbac237e3,0xb4a53913,0xb8483af6,0xbb0e3bf6,0xbb503bfa,0x378bae46,0x367c2cb5,
0x3bfeba6d,0x3a0fb179,0x2a48b8c4,0x393abbe2,0x36d7badd,0x3a4fbbff,0xbb3b381d,0xb8eca648,0xb95f30b2,0xb732b303,0xb9ed3bea,0xbb253bce,
0xbb883bc3,0xbbb63b50,0x356433c6,0x3444367c,0x323e3872,0xb7323bce,0x3bd9baa7,0x3b25b303,0x3bd9baa7,0x3bb6b67c,0xb23eb872,0x3444bb50,
0xb23eb872,0x2cb5ba8a,0xbbd93aa7,0xbbfa389b,0xbbd93aa7,0xbbf139cb,0x323e3872,0x2fd63984,0xbb3b3add,0xbbce3444,0x36d7381d,0xb3033bb6,
0x39ed30b2,0x35c2393a,0x395fbbea,0x3b77ba0f,0x3564bbc3,0x389bbbf1,0xbb8833c6,0xba8aafd6,0xbbfe38c4,0xbbff3732,0x2a483a6d,0xa6483b25,
0xb913b78b,0xa648bb99,0xba2f3b0e,0xbbff3505,0xae463ba8,0xb8483bb6,0x3bf6b4a5,0x3ac23444,0x3a2fbb0e,0x3b50b93a,0xb913b78b,0xb67cba0f,
0xbbf634a5,0xbbe22fd6,0xae463ba8,0xb1793bf1,0x38c4bb3b,0x3bb6b5c2,0xba6db6d7,0xb444bb77,0xbadd395f,0xbbfa3179,0x381d39ed,0x2cb53be2,
0x3beab564,0x3bf12648,0xb0b2bb88,0x2fd6bbff,0xbbc3aa48,0xbb99b303,0xb3c63bfe,0xb5053bce,0x3b64361f,0x37e33b50,0x361fbb64,0x3af6b67c,
0xbb64b61f,0xb93aba8a,0xb61f3b64,0xba0f389b,0x3b64361f,0x3a4f3984,0x361fbb64,0x38ecb9cb,0xbb64b61f,0xbb25b848,0xb61f3b64,0xb7323ac2,
0xb0b23b88,0xb9cb3732,0x3bea3564,0x39843b25,0xb3c6bbfe,0x3303baf6,0xbbc32a48,0xbbceb7e3,0x38c43b3b,0x35c23bfa,0x3a6db6d7,0x3b77acb5,
0xbaddb95f,0xba8aba4f,0xb81d39ed,0xb89b38ec,0xbbf6b4a5,0xbac2baf6,0x2e463ba8,0xb84837e3,0x3913b78b,0x3b502cb5,0xba2fbb0e,0xb67cbbfa,
0x2e463ba8,0xb1793a4f,0x3bf634a5,0x3be238ec,0xba2fbb0e,0xb9cbbb99,0xb913378b,0xb9843505,0xb564bbc3,0x3505b848,0xbb88b3c6,0xbb99bac2,
0x3bfe38c4,0x3af63b77,0x2a48ba6d,0x37e3b5c2,0xb6d7381d,0xb93a3179,0x3b3b3add,0x3a0f3be2,0xb95fbbea,0xb8ecbbff,0xb9ed30b2,0xba4fa648,
0x3aa7323e,0x3bfa3a8a,0xb872bbd9,0x2cb5b89b,0x38723bd9,0x2fd639cb,0x3aa7323e,0x3bf13984,0xbaa7b23e,0xbb99b848,0x38723bd9,0x35053ac2,
0xb872bbd9,0xb7e3bb77,0xbaa7b23e,0xbaf6b5c2,0x39ed3bea,0x317938ec,0x395f30b2,0x3be23a4f,0xb56433c6,0xb9cbb505,0x3b883bc3,0x39843b99,
0xbbfeba6d,0xbbcebbb6,0x2a4838c4,0xb3033444,0xb6d7badd,0xb5c2ba0f,0xbb3bb81d,0xbb77b93a,0xb78bae46,0xbb50ba0f,0x3b0e3bf6,0x367c393a,
0xbba8ba2f,0xbbe2bbf1,0x34a53913,0xb1792fd6,0xbb0ebbf6,0xb9cbbb25,0xb78bae46,0xb984b732,0xb4a5b913,0xb303b7e3,0xbba8ba2f,0xbbcebaf6,
0xbbc3bbfe,0xb8ecb984,0xb3c6aa48,0xba4fb9cb,0xba6dbb3b,0xb732b848,0xb8c4b6d7,0xbb25bac2,0xb81db95f,0xb444b5c2,0xbaddb9ed,0xbbb6bb77,
0xb0b2b564,0xacb5b179,0xbbeabb88,0xbbfabbe2,0x3c003c00,0x96480000,0x3c003c00,0xa311a248,0x3c003c00,0x9cb69a48,0x3c003c00,0xa452a3db,
0x3c003c00,0x9fdb9e48,0x3c003c00,0xa51ba4b6,0x3c003c00,0xa17fa0b6,0x3bff3c00,0xa5e4a57f,0x3c003c00,0x9fdb0000,0x3bfb3bfc,0xac6aabd9,
0x3bff3c00,0xa5e4a3db,0x3bf93bfa,0xad65ace7,0x3bfe3bff,0xa8e8a7da,0x3bf63bf7,0xae5fade2,0x3bfd3bfe,0xaadea9e3,0x3bf23bf4,0xaf59aedc,
0x3c003c00,0xa3110000,0x3bf03bf4,0xafefaf0e,0x3bfe3bff,0xa94da711,0x3be83bed,0xb0d7b067,0x3bfb3bfd,0xac6aab11,0x3bdf3be4,0xb1b6b147,
0x3bf63bf9,0xae2dad4c,0x3bd43bda,0xb294b226,0x3c003c00,0xa51b0000,0x3bdf3be6,0xb1b6b115,0x3bfc3bfe,0xaba7a91b,0x3bcf3bd7,0xb2f7b257,
0x3bf63bf9,0xae5fad1a,0x3bbc3bc6,0xb41ab396,0x3bec3bf1,0xb074afa4,0x3ba53bb1,0xb4b7b469,0x3bff3c00,0xa6ad0000,0x3bc83bd4,0xb371b2a1,
0x3bfa3bfd,0xad00aaac,0x3bac3bbb,0xb487b420,0x3bef3bf5,0xb029aeaa,0x3b8b3b9d,0xb552b4ed,0x3bde3be7,0xb1cfb0fd,0x3b653b79,0xb61ab5b6,
0x3bff3c00,0xa81f0000,0x3bab3bbc,0xb493b414,0x3bf63bfc,0xae2dac1f,0x3b813b97,0xb58db511,0x3be53bef,0xb122b01d,0x3b4f3b69,0xb682b608,
0x3bcc3bda,0xb328b226,0x3b163b33,0xb76fb6f9,0x3bfe3c00,0xa8e80000,0x3b873ba0,0xb56ab4d5,0x3bf23bfa,0xaf59ace7,0x3b4c3b6b,0xb68db5fd,
0x3bda3be8,0xb219b0e4,0x3b073b2b,0xb7a6b71b,0x3bb73bca,0xb43eb34c,0x3ab63ae0,0xb85ab817,0x3bfe3c00,0xa9b10000,0x3b5e3b80,0xb63cb593,
0x3bee3bf8,0xb042adb0,0x3b103b39,0xb785b6e3,0x3bce3be0,0xb30fb1aa,0x3ab33ae3,0xb85fb812,0x3b9e3bb7,0xb4e7b438,0x3a493a7f,0xb8f3b8ab,
0x3bfd3c00,0xaa7a0000,0x3b2f3b5a,0xb70ab64e,0x3be83bf6,0xb0d7ae78,0x3acb3aff,0xb83ab7c2,0x3bbf3bd6,0xb402b26f,0x3a543a92,0xb8e5b891,
0x3b813ba2,0xb58db4c9,0x39cd3a13,0xb982b935,0x3bfd3c00,0xab430000,0x3afb3b30,0xb7d2b705,0x3be23bf3,0xb16caf40,0x3a7e3abf,0xb8adb84d,
0x3bae3bcb,0xb47bb334,0x39eb3a37,0xb962b909,0x3b603b8a,0xb631b558,0x3946399b,0xba04b9b5,0x3bfc3c00,0xac060000,0x3ac13b02,0xb84ab7b7,
0x3bdc3bf0,0xb201b004,0x3a293a78,0xb91bb8b5,0x3b9c3bc0,0xb4f3b3f7,0x397939d4,0xb9d6b97b,0x3b3d3b70,0xb6d2b5e5,0x38b23918,0xba7aba2b,
0x3bfb3c00,0xac6a0000,0x3a813ad0,0xb8a8b832,0x3bd43bed,0xb294b067,0x39cd3a2b,0xb982b918,0x3b873bb2,0xb56ab45d,0x38fd3969,0xba41b9e5,
0x3b163b53,0xb76fb670,0x3815388c,0xbae1ba95,0x3bfa3c00,0xacce0000,0x3a3d3a99,0xb902b887,0x3bcc3be9,0xb328b0cb,0x396b39d8,0xb9e3b976,
0x3b713ba4,0xb5dfb4bd,0x387a38f6,0xbaa2ba47,0x3aeb3b33,0xb805b6f9,0x36dd37ee,0xbb3abaf3,0x3bf93c00,0xad330000,0x39f43a5e,0xb958b8d8,
0x3bc33be5,0xb3bab12e,0x39023980,0xba3db9d0,0x3b593b95,0xb654b51d,0x37dd387c,0xbaf7baa0,0x3abd3b11,0xb850b780,0x358136b5,0xbb83bb43,
0x3bf83c00,0xad970000,0x39a63a1f,0xb9aab927,0x3bba3be1,0xb426b191,0x38943922,0xba90ba23,0x3b3f3b84,0xb6c6b57c,0x36bb37f9,0xbb42baf0,
0x3a8c3aed,0xb899b802,0x341a3570,0xbbbcbb86,0x3bf73c00,0xadfb0000,0x395439dc,0xb9f8b972,0x3bb03bdc,0xb46fb1f4,0x382038bf,0xbadbba71,
0x3b243b72,0xb737b5da,0x358d36ee,0xbb81bb36,0x3a583ac6,0xb8e0b842,0x31533420,0xbbe3bbbb,0x3bf63c00,0xae5f0000,0x38fd3996,0xba41b9ba,
0x3ba53bd7,0xb4b7b257,0x374e3858,0xbb1ebab8,0x3b073b5f,0xb7a6b637,0x345735da,0xbbb3bb72,0x3a213a9c,0xb924b881,0x2cce3191,0xbbfabbe1,
0x3bf53c00,0xaec30000,0x38a3394d,0xba85b9fe,0x3b9a3bd2,0xb4ffb2b9,0x365437d8,0xbb59baf9,0x3ae83b4b,0xb80ab693,0x323234bd,0xbbd9bba4,
0x39e73a71,0xb966b8bf,0xa4522db0,0xbc00bbf8,0x3bf33c00,0xaf270000,0x38453900,0xbac4ba3f,0x3b8e3bcd,0xb546b31b,0x355236f9,0xbb8bbb33,
0x3ac73b36,0xb840b6ee,0x2f593334,0xbbf2bbcb,0x39aa3a43,0xb9a6b8fb,0xaef51a48,0xbbf4bc00,0x3bf23c00,0xaf8b0000,0x37c838b0,0xbafeba7c,
0x3b813bc7,0xb58db37d,0x344b3614,0xbbb5bb67,0x3aa53b20,0xb874b748,0x288430e4,0xbbffbbe8,0x396b3a13,0xb9e3b935,0xb263ad4c,0xbbd7bbf9,
0x3bf03c00,0xafef0000,0x36ff385d,0xbb32bab5,0x3b733bc1,0xb5d4b3df,0x327c3529,0xbbd6bb93,0x3a813b08,0xb8a8b7a1,0xa9b12d1a,0xbbfebbf9,
0x392939e1,0xba1db96d,0xb49fb160,0xbba9bbe3,0x3bef3c00,0xb0290000,0x36313807,0xbb60bae9,0x3b653bbb,0xb61ab420,0x305b3438,0xbbedbbb7,
0x3a5c3af0,0xb8dbb7f9,0xafef1e48,0xbbf0bc00,0x38e539ad,0xba54b9a4,0xb602b408,0xbb6abbbe,0x3bed3c00,0xb05b0000,0x355e375e,0xbb89bb1a,
0x3b573bb4,0xb65fb451,0x2c6a3288,0xbbfbbbd5,0x3a353ad6,0xb90cb828,0xb27cac51,0xbbd6bbfb,0x389e3976,0xba89b9d8,0xb759b558,0xbb1bbb8a,
0x3beb3c00,0xb08d0000,0x348736aa,0xbbacbb46,0x3b473bad,0xb6a4b481,0x16483099,0xbc00bbeb,0x3a0d3abc,0xb93cb852,0xb47bb080,0xbbaebbec,
0x3855393e,0xbababa0b,0xb850b69e,0xbabdbb49,0x3be93c00,0xb0be0000,0x335935f1,0xbbc9bb6e,0x3b373ba6,0xb6e8b4b1,0xac382d4c,0xbbfcbbf9,
0x39e33aa0,0xb96bb87c,0xb5b1b2d2,0xbb7abbd1,0x380a3905,0xbae8ba3b,0xb8eab7d8,0xba50baf9,0x3be73c00,0xb0f00000,0x319e3534,0xbbe0bb91,
0x3b273b9e,0xb72cb4e1,0xb042257f,0xbbeebc00,0x39b83a83,0xb999b8a6,0xb6ddb48d,0xbb3abbab,0x377a38c9,0xbb13ba69,0xb979b881,0xb9d6ba9c,
0x3be53c00,0xb1220000,0x2fbd3475,0xbbf1bbaf,0x3b163b97,0xb76fb511,0xb263a91b,0xbbd7bbfe,0x398b3a65,0xb9c5b8ce,0xb7feb5ab,0xbaeebb7b,
0x36dd388c,0xbb3aba95,0xb9fcb90e,0xb94fba33,0x3be33c00,0xb1530000,0x2c383365,0xbbfcbbc9,0x3b043b8f,0xb7b2b540,0xb43eae78,0xbbb7bbf6,
0x395d3a47,0xb9f0b8f6,0xb889b6c1,0xba97bb41,0x363c384d,0xbb5ebabf,0xba73b992,0xb8bcb9be,0x3be13c00,0xb1850000,0x217f31db,0xbc00bbdd,
0x3af13b86,0xb7f3b570,0xb546b12e,0xbb8ebbe5,0x392e3a27,0xba19b91d,0xb90cb7cd,0xba35bafc,0x3599380d,0xbb7fbae6,0xbadbba0b,0xb820b93e,
0x3bdf3c00,0xb1b60000,0xa9b1304e,0xbbfebbed,0x3ade3b7d,0xb81ab59f,0xb648b31b,0xbb5cbbcd,0x38fd3a07,0xba41b943,0xb986b867,0xb9c9baae,
0x34f33796,0xbb9cbb0b,0xbb35ba78,0xb6f4b8b5,0x3bdd3c00,0xb1e80000,0xae5f2d7e,0xbbf6bbf8,0x3acb3b74,0xb83ab5ce,0xb742b481,0xbb21bbad,
0x38cc39e5,0xba67b969,0xb9f8b8e2,0xb954ba56,0x344b3710,0xbbb5bb2e,0xbb7fbad9,0xb599b822,0x3bda3c00,0xb2190000,0xb0f028b6,0xbbe7bbff,
0x3ab63b6b,0xb85ab5fd,0xb81ab570,0xbadebb86,0x389939c3,0xba8cb98d,0xba60b956,0xb8d6b9f6,0x33403687,0xbbcbbb4e,0xbbb8bb2e,0xb432b710,
0x3bff3bff,0xa6ada648,0x3bfe3bff,0xa8e8a8b6,0x3bff3bff,0xa776a711,0x3bfe3bfe,0xa94da91b,0x3bff3bff,0xa81fa7da,0x3bfe3bfe,0xa9b1a97f,
0x3bff3bff,0xa884a852,0x3bfe3bfe,0xaa16a9e3,0x3bef3bf1,0xb029afd6,0x3bda3bdd,0xb219b1db,0x3bea3bed,0xb0a6b067,0x3bd43bd7,0xb294b257,
0x3be53be8,0xb122b0e4,0x3bce3bd1,0xb30fb2d2,0x3be03be3,0xb19eb160,0x3bc63bca,0xb389b34c,0x3bc83bce,0xb371b303,0x3b873b91,0xb56ab534,
0x3bba3bc1,0xb426b3df,0x3b733b7d,0xb5d4b59f,0x3bab3bb2,0xb493b45d,0x3b5e3b69,0xb63cb608,0x3b9a3ba2,0xb4ffb4c9,0x3b473b53,0xb6a4b670,
0x3b8b3b99,0xb552b505,0x3b073b1a,0xb7a6b75e,0x3b6f3b7d,0xb5ebb59f,0x3ade3af3,0xb81ab7ee,0x3b4f3b5f,0xb682b637,0x3ab33ac9,0xb85fb83d,
0x3b2c3b3e,0xb715b6cc,0x3a853a9c,0xb8a3b881,0x3b3a3b50,0xb6ddb67c,0x3a5c3a7c,0xb8dbb8b0,0x3b0a3b22,0xb79bb73d,0x3a193a3b,0xb92eb905,
0x3ad53af0,0xb82ab7f9,0x39d239f6,0xb97db956,0x3a9b3ab8,0xb884b858,0x398639ad,0xb9c9b9a4,0x3ad53af6,0xb82ab7e3,0x398b39ba,0xb9c5b996,
0x3a8c3ab1,0xb899b862,0x3929395b,0xba1db9f2,0x3a3d3a65,0xb902b8ce,0x38c138f6,0xba6fba47,0x39e73a13,0xb966b935,0x3855388c,0xbababa95,
0x3a5c3a8a,0xb8dbb89b,0x389938d8,0xba8cba5e,0x39f83a2b,0xb954b918,0x38153858,0xbae1bab8,0x398b39c3,0xb9c5b98d,0x371537a1,0xbb2cbb08,
0x39163951,0xba2db9fa,0x35f73687,0xbb6cbb4e,0x39d23a0f,0xb97db93a,0x371537b7,0xbb2cbb02,0x394f3992,0xb9fcb9be,0x35c83670,0xbb76bb53,
0x38c13909,0xba6fba37,0x346f351d,0xbbb0bb95,0x382a3877,0xbad5baa3,0x3219337d,0xbbdabbc7,0x39373984,0xba11b9cb,0x34cf3593,0xbba1bb80,
0x389438e7,0xba90ba52,0x327c3408,0xbbd6bbbe,0x37c8383d,0xbafebac9,0x2e9130e4,0xbbf5bbe8,0x36543710,0xbb59bb2e,0x16482aac,0xbc00bbfd,
0x388e38ec,0xba93ba4f,0x30d732a1,0xbbe8bbd4,0x3790382d,0xbb0dbad3,0x28e82e14,0xbbfebbf7,0x35eb36c1,0xbb6fbb41,0xaccea4b6,0xbbfabc00,
0x34323511,0xbbb8bb97,0xb201b036,0xbbdcbbee,0x37b23848,0xbb04bac2,0x96482bd9,0xbc00bbfc,0x35df36cc,0xbb71bb3e,0xb010ac1f,0xbbefbbfc,
0x33eb34ed,0xbbc0bb9d,0xb402b20d,0xbbbfbbdb,0x2fef31f4,0xbbf0bbdc,0xb5ebb4f9,0xbb6fbb9b,0x36313732,0xbb60bb25,0xb0f0ad7e,0xbbe7bbf8,
0x341a3529,0xbbbcbb93,0xb49fb31b,0xbba9bbcd,0x2fbd320d,0xbbf1bbdb,0xb6afb5ab,0xbb45bb7b,0xa4522aac,0xbc00bbfd,0xb850b7ac,0xbabdbb05,
0x349f35c2,0xbba9bb77,0xb4dbb365,0xbb9fbbc9,0x308d32ea,0xbbebbbd0,0xb715b5fd,0xbb2cbb6b,0x9fdb2c51,0xbc00bbfb,0xb894b812,0xba90bae3,
0xb109ad4c,0xbbe6bbf9,0xb982b90e,0xb9cdba33,0x32013444,0xbbdcbbb6,0xb721b5f1,0xbb2abb6e,0x26ad2edc,0xbbffbbf4,0xb8adb822,0xba7ebad9,
0xb05bab11,0xbbedbbfd,0xb9aab930,0xb9a6ba17,0xb4b7b2ea,0xbba5bbd0,0xba81ba1b,0xb8a8b92b,0x2d653179,0xbbf9bbe2,0xb89eb807,0xba89bae9,
0xadc99a48,0xbbf8bc00,0xb9afb92b,0xb9a1ba1b,0xb432b1aa,0xbbb8bbe0,0xba93ba27,0xb88eb91d,0xb6d2b587,0xbb3dbb82,0xbb45baf3,0xb6afb7ee,
0xa51b2cb5,0xbc00bbfa,0xb990b900,0xb9c0ba3f,0xb294af40,0xbbd4bbf3,0xba89ba13,0xb89eb935,0xb625b4bd,0xbb63bba4,0xbb47baf0,0xb6a4b7f9,
0xb865b780,0xbab0bb11,0xbbc5bb8f,0xb3a2b540,0xafefa648,0xbbf0bbff,0xba60b9dc,0xb8d6b972,0xb517b31b,0xbb96bbcd,0xbb35bad3,0xb6f4b82d,
0xb7feb693,0xbaeebb4b,0xbbc0bb84,0xb3ebb57c,0xb94ab8ab,0xba00ba7f,0xbbfdbbe9,0xaa7ab0cb,0xb340afd6,0xbbcbbbf1,0xbb0aba99,0xb79bb887,
0xb6d2b540,0xbb3dbb8f,0xbbaebb67,0xb47bb614,0xb8dbb828,0xba5cbad6,0xbbfbbbe0,0xac9cb1aa,0xba15b980,0xb933b9d0,0xbbecbbff,0x30742852,
0xb53ab303,0xbb90bbce,0xbb89bb30,0xb55eb705,0xb83ab6e3,0xbacbbb39,0xbbf2bbca,0xaf8bb34c,0xb9a1b8f6,0xb9afba47,0xbbf5bc00,0x2ec39e48,
0xbac1ba3b,0xb84ab905,0xbb92bbd0,0x352f32ea,0xb6c6b505,0xbb3fbb99,0xbbdcbba0,0xb201b4d5,0xb8fdb838,0xba41bacc,0xbbfebbfb,0x2a16ac83,
0xba50b9b1,0xb8eab99f,0xbbaebbe4,0x347b3147,0xbb4abad9,0xb699b822,0xbaf1bb5d,0x37f33642,0xb820b67c,0xbadbbb50,0xbbffbbe6,0xa884b115,
0xb9afb8f1,0xb9a1ba4b,0xbbd2bbf8,0x32c62db0,0xbae5ba56,0xb80fb8e2,0xbb2abb8c,0x3721354c,0xbbaebb58,0xb47bb659,0xba11baaa,0x3937386d,
0xb8d1b7e3,0xba64baf6,0xbbf2bc00,0x2f8ba248,0xba4db99b,0xb8eeb9b5,0xbb6fbbc1,0x35eb33df,0xbb5cbae3,0xb648b812,0xba6bbafc,0x38c737cd,
0xbbebbbb4,0xb08db451,0xb8f8b9be,0x3a453992,0xb974b89b,0xb9daba8a,0xbbb5bbed,0x344b304e,0xbad5ba33,0xb82ab90e,0xbad8bb58,0x38253659,
0xbbb3bb55,0xb457b665,0xb979ba37,0x39d63909,0xbc00bbed,0x9648b067,0xb764b8a0,0x3b183a87,0xba09b93a,0xb941ba0f,0xbb4abbaf,0x36993475,
0xbb45bab8,0xb6afb858,0xba11babf,0x3937384d,0xbbeabbab,0xb0a6b48d,0xb85ab943,0x3ab63a07,0xbbecbc00,0x30749a48,0xb493b6b5,0x3bab3b43,
0xba8cb9cb,0xb899b984,0xbab3bb46,0x385f36aa,0xbb9cbb28,0xb4f3b726,0xb91fb9fa,0x3a253951,0xbc00bbe4,0xa452b147,0xb631b828,0x3b603ad6,
0xbbb0bbee,0x346f3036,0xae5fb3df,0x3bf63bc1,0xbafeba4f,0xb7c8b8ec,0xb9f4bab5,0x3958385d,0xbbd8bb82,0xb24bb587,0xb80ab90e,0x3ae83a33,
0xbbf3bbfe,0x2f27a97f,0xb2f7b5da,0x3bcf3b72,0xbb4cbbb7,0x368d3438,0x2dc9ac1f,0x3bf83bfc,0xbb5cbac2,0xb648b848,0xb911b9fe,0x3a31394d,
0xbbf9bbc4,0xad33b3ae,0xb5b1b802,0x3b7a3aed,0xbbc5bbf9,0x33a22d1a,0xa94db26f,0x3bfe3bd6,0xbac4bb5d,0x38453642,0x346f2fa4,0x3bb03bf1,
0xbba5bb25,0xb4b7b732,0xb80fb927,0x3ae53a1f,0xbbffbbee,0x2884b036,0xb24bb5b6,0x3bd83b79,0xbb76bbd6,0x35c8326f,0x305ba7da,0x3bed3bff,
0xba19bae0,0x392e3817,0x374234c9,0x3b213ba2,0xbbd9bb77,0xb232b5c2,0xb5ebb832,0x3b6f3ad0,0xbbe8bc00,0x30d7a57f,0xa81fb288,0x3bff3bd5,
0xbb07bb95,0x37a6351d,0x34f33080,0x3b9c3bec,0xb94fba43,0x39fc38fb,0x38ea3780,0x3a503b11,0xbbf8bbb6,0xadc9b444,0xb328b64e,0x3bcc3b5a,
0xbbb7bbf8,0x343e2db0,0x3042a9e3,0x3bee3bfe,0xba7abb36,0x38b236ee,0x379034ed,0x3b0d3b9d,0xb86ab989,0x3aac39c7,0x3a0438fb,0x39463a43,
0xbc00bbe2,0x2311b179,0xac9cb414,0x3bfb3bbc,0xbb6abbd7,0x36023257,0x34b72f40,0x3ba53bf3,0xb9d2babc,0x397d3852,0x38f83775,0x3a453b14,
0xb6ddb8b5,0x3b3a3a78,0x3ae83a0b,0x380a393e,0xbbf2bbfa,0x2f8bacb5,0x2d33af0e,0x3bf93bf4,0xbb04bb9e,0x37b234e1,0x372c3451,0x3b273bb4,
0xb911ba27,0x3a31391d,0x3a0038e2,0x394a3a56,0xb4c3b796,0x3ba33b0b,0x3b8b3ae6,0x3552380d,0x4c004c00,0x26480000,0x4c004c00,0x33113248,
0x4c004c00,0x2cb62a48,0x4c004c00,0x345233db,0x4c004c00,0x2fdb2e48,0x4c004c00,0x351b34b6,0x4c004c00,0x317f30b6,0x4bff4c00,0x35e4357f,
0x4c004c00,0x2fdb0000,0x4bfb4bfc,0x3c6a3bd9,0x4bff4c00,0x35e433db,0x4bf94bfa,0x3d653ce7,0x4bfe4bff,0x38e837da,0x4bf64bf7,0x3e5f3de2,
0x4bfd4bfe,0x3ade39e3,0x4bf24bf4,0x3f593edc,0x4c004c00,0x33110000,0x4bf04bf4,0x3fef3f0e,0x4bfe4bff,0x394d3711,0x4be84bed,0x40d74067,
0x4bfb4bfd,0x3c6a3b11,0x4bdf4be4,0x41b64147,0x4bf64bf9,0x3e2d3d4c,0x4bd44bda,0x42944226,0x4c004c00,0x351b0000,0x4bdf4be6,0x41b64115,
0x4bfc4bfe,0x3ba7391b,0x4bcf4bd7,0x42f74257,0x4bf64bf9,0x3e5f3d1a,0x4bbc4bc6,0x441a4396,0x4bec4bf1,0x40743fa4,0x4ba54bb1,0x44b74469,
0x4bff4c00,0x36ad0000,0x4bc84bd4,0x437142a1,0x4bfa4bfd,0x3d003aac,0x4bac4bbb,0x44874420,0x4bef4bf5,0x40293eaa,0x4b8b4b9d,0x455244ed,
0x4bde4be7,0x41cf40fd,0x4b654b79,0x461a45b6,0x4bff4c00,0x381f0000,0x4bab4bbc,0x44934414,0x4bf64bfc,0x3e2d3c1f,0x4b814b97,0x458d4511,
0x4be54bef,0x4122401d,0x4b4f4b69,0x46824608,0x4bcc4bda,0x43284226,0x4b164b33,0x476f46f9,0x4bfe4c00,0x38e80000,0x4b874ba0,0x456a44d5,
0x4bf24bfa,0x3f593ce7,0x4b4c4b6b,0x468d45fd,0x4bda4be8,0x421940e4,0x4b074b2b,0x47a6471b,0x4bb74bca,0x443e434c,0x4ab64ae0,0x485a4817,
0x4bfe4c00,0x39b10000,0x4b5e4b80,0x463c4593,0x4bee4bf8,0x40423db0,0x4b104b39,0x478546e3,0x4bce4be0,0x430f41aa,0x4ab34ae3,0x485f4812,
0x4b9e4bb7,0x44e74438,0x4a494a7f,0x48f348ab,0x4bfd4c00,0x3a7a0000,0x4b2f4b5a,0x470a464e,0x4be84bf6,0x40d73e78,0x4acb4aff,0x483a47c2,
0x4bbf4bd6,0x4402426f,0x4a544a92,0x48e54891,0x4b814ba2,0x458d44c9,0x49cd4a13,0x49824935,0x4bfd4c00,0x3b430000,0x4afb4b30,0x47d24705,
0x4be24bf3,0x416c3f40,0x4a7e4abf,0x48ad484d,0x4bae4bcb,0x447b4334,0x49eb4a37,0x49624909,0x4b604b8a,0x46314558,0x4946499b,0x4a0449b5,
0x4bfc4c00,0x3c060000,0x4ac14b02,0x484a47b7,0x4bdc4bf0,0x42014004,0x4a294a78,0x491b48b5,0x4b9c4bc0,0x44f343f7,0x497949d4,0x49d6497b,
0x4b3d4b70,0x46d245e5,0x48b24918,0x4a7a4a2b,0x4bfb4c00,0x3c6a0000,0x4a814ad0,0x48a84832,0x4bd44bed,0x42944067,0x49cd4a2b,0x49824918,
0x4b874bb2,0x456a445d,0x48fd4969,0x4a4149e5,0x4b164b53,0x476f4670,0x4815488c,0x4ae14a95,0x4bfa4c00,0x3cce0000,0x4a3d4a99,0x49024887,
0x4bcc4be9,0x432840cb,0x496b49d8,0x49e34976,0x4b714ba4,0x45df44bd,0x487a48f6,0x4aa24a47,0x4aeb4b33,0x480546f9,0x46dd47ee,0x4b3a4af3,
0x4bf94c00,0x3d330000,0x49f44a5e,0x495848d8,0x4bc34be5,0x43ba412e,0x49024980,0x4a3d49d0,0x4b594b95,0x4654451d,0x47dd487c,0x4af74aa0,
0x4abd4b11,0x48504780,0x458146b5,0x4b834b43,0x4bf84c00,0x3d970000,0x49a64a1f,0x49aa4927,0x4bba4be1,0x44264191,0x48944922,0x4a904a23,
0x4b3f4b84,0x46c6457c,0x46bb47f9,0x4b424af0,0x4a8c4aed,0x48994802,0x441a4570,0x4bbc4b86,0x4bf74c00,0x3dfb0000,0x495449dc,0x49f84972,
0x4bb04bdc,0x446f41f4,0x482048bf,0x4adb4a71,0x4b244b72,0x473745da,0x458d46ee,0x4b814b36,0x4a584ac6,0x48e04842,0x41534420,0x4be34bbb,
0x4bf64c00,0x3e5f0000,0x48fd4996,0x4a4149ba,0x4ba54bd7,0x44b74257,0x474e4858,0x4b1e4ab8,0x4b074b5f,0x47a64637,0x445745da,0x4bb34b72,
0x4a214a9c,0x49244881,0x3cce4191,0x4bfa4be1,0x4bf54c00,0x3ec30000,0x48a3494d,0x4a8549fe,0x4b9a4bd2,0x44ff42b9,0x465447d8,0x4b594af9,
0x4ae84b4b,0x480a4693,0x423244bd,0x4bd94ba4,0x49e74a71,0x496648bf,0xb4523db0,0x4c004bf8,0x4bf34c00,0x3f270000,0x48454900,0x4ac44a3f,
0x4b8e4bcd,0x4546431b,0x455246f9,0x4b8b4b33,0x4ac74b36,0x484046ee,0x3f594334,0x4bf24bcb,0x49aa4a43,0x49a648fb,0xbef52a48,0x4bf44c00,
0x4bf24c00,0x3f8b0000,0x47c848b0,0x4afe4a7c,0x4b814bc7,0x458d437d,0x444b4614,0x4bb54b67,0x4aa54b20,0x48744748,0x388440e4,0x4bff4be8,
0x496b4a13,0x49e34935,0xc263bd4c,0x4bd74bf9,0x4bf04c00,0x3fef0000,0x46ff485d,0x4b324ab5,0x4b734bc1,0x45d443df,0x427c4529,0x4bd64b93,
0x4a814b08,0x48a847a1,0xb9b13d1a,0x4bfe4bf9,0x492949e1,0x4a1d496d,0xc49fc160,0x4ba94be3,0x4bef4c00,0x40290000,0x46314807,0x4b604ae9,
0x4b654bbb,0x461a4420,0x405b4438,0x4bed4bb7,0x4a5c4af0,0x48db47f9,0xbfef2e48,0x4bf04c00,0x48e549ad,0x4a5449a4,0xc602c408,0x4b6a4bbe,
0x4bed4c00,0x405b0000,0x455e475e,0x4b894b1a,0x4b574bb4,0x465f4451,0x3c6a4288,0x4bfb4bd5,0x4a354ad6,0x490c4828,0xc27cbc51,0x4bd64bfb,
0x489e4976,0x4a8949d8,0xc759c558,0x4b1b4b8a,0x4beb4c00,0x408d0000,0x448746aa,0x4bac4b46,0x4b474bad,0x46a44481,0x26484099,0x4c004beb,
0x4a0d4abc,0x493c4852,0xc47bc080,0x4bae4bec,0x4855493e,0x4aba4a0b,0xc850c69e,0x4abd4b49,0x4be94c00,0x40be0000,0x435945f1,0x4bc94b6e,
0x4b374ba6,0x46e844b1,0xbc383d4c,0x4bfc4bf9,0x49e34aa0,0x496b487c,0xc5b1c2d2,0x4b7a4bd1,0x480a4905,0x4ae84a3b,0xc8eac7d8,0x4a504af9,
0x4be74c00,0x40f00000,0x419e4534,0x4be04b91,0x4b274b9e,0x472c44e1,0xc042357f,0x4bee4c00,0x49b84a83,0x499948a6,0xc6ddc48d,0x4b3a4bab,
0x477a48c9,0x4b134a69,0xc979c881,0x49d64a9c,0x4be54c00,0x41220000,0x3fbd4475,0x4bf14baf,0x4b164b97,0x476f4511,0xc263b91b,0x4bd74bfe,
0x498b4a65,0x49c548ce,0xc7fec5ab,0x4aee4b7b,0x46dd488c,0x4b3a4a95,0xc9fcc90e,0x494f4a33,0x4be34c00,0x41530000,0x3c384365,0x4bfc4bc9,
0x4b044b8f,0x47b24540,0xc43ebe78,0x4bb74bf6,0x495d4a47,0x49f048f6,0xc889c6c1,0x4a974b41,0x463c484d,0x4b5e4abf,0xca73c992,0x48bc49be,
0x4be14c00,0x41850000,0x317f41db,0x4c004bdd,0x4af14b86,0x47f34570,0xc546c12e,0x4b8e4be5,0x492e4a27,0x4a19491d,0xc90cc7cd,0x4a354afc,
0x4599480d,0x4b7f4ae6,0xcadbca0b,0x4820493e,0x4bdf4c00,0x41b60000,0xb9b1404e,0x4bfe4bed,0x4ade4b7d,0x481a459f,0xc648c31b,0x4b5c4bcd,
0x48fd4a07,0x4a414943,0xc986c867,0x49c94aae,0x44f34796,0x4b9c4b0b,0xcb35ca78,0x46f448b5,0x4bdd4c00,0x41e80000,0xbe5f3d7e,0x4bf64bf8,
0x4acb4b74,0x483a45ce,0xc742c481,0x4b214bad,0x48cc49e5,0x4a674969,0xc9f8c8e2,0x49544a56,0x444b4710,0x4bb54b2e,0xcb7fcad9,0x45994822,
0x4bda4c00,0x42190000,0xc0f038b6,0x4be74bff,0x4ab64b6b,0x485a45fd,0xc81ac570,0x4ade4b86,0x489949c3,0x4a8c498d,0xca60c956,0x48d649f6,
0x43404687,0x4bcb4b4e,0xcbb8cb2e,0x44324710,0x4bd84c00,0x424b0000,0xc2adb248,0x4bd34c00,0x4aa24b62,0x487a462b,0xc88ec659,0x4a934b58,
0x4865499f,0x4ab049b1,0xcabdc9c3,0x4850498d,0x41e845fd,0x4bdd4b6b,0xcbe1cb74,0x418545ce,0x4bd64c00,0x427c0000,0xc432bbd9,0x4bb84bfc,
0x4a8c4b58,0x48994659,0xc8fdc73d,0x4a414b22,0x4830497b,0x4ad149d4,0xcb10ca27,0x4785491d,0x408d4570,0x4beb4b86,0xcbf9cbad,0x3d334481,
0x4bd34c00,0x42ad0000,0xc50bbf0e,0x4b984bf4,0x4a764b4e,0x48b74687,0xc966c80d,0x49e74ae6,0x47f34956,0x4af149f6,0xcb57ca83,0x465f48a6,
0x3e5f44e1,0x4bf64b9e,0xcc00cbd7,0xb17f4257,0x4bd04c00,0x42de0000,0xc5dfc115,0x4b714be6,0x4a604b43,0x48d646b5,0xc9c9c877,0x49864aa3,
0x47854930,0x4b104a17,0xcb92cad6,0x452f4828,0x3b434451,0x4bfd4bb4,0xcbf5cbf3,0xbe913f40,0x4bce4c00,0x430f0000,0xc6afc2a1,0x4b454bd4,
0x4a494b39,0x48f346e3,0xca25c8dd,0x491f4a5a,0x47154909,0x4b2c4a37,0xcbc0cb20,0x43eb4748,0x3311437d,0x4c004bc7,0xcbd9cbff,0xc2323711,
0x4bcb4c00,0x43400000,0xc77ac414,0x4b134bbc,0x4a314b2e,0x49114710,0xca7ac93e,0x48b24a0b,0x46a448e2,0x4b474a56,0xcbe2cb5f,0x416c4637,
0xb7764257,0x4bff4bd7,0xcbaccbfd,0xc487bb75,0x4bc84c00,0x43710000,0xc820c4d5,0x4adb4ba0,0x4a194b22,0x492e473d,0xcac7c99b,0x484049b5,
0x463148ba,0x4b604a74,0xcbf8cb95,0x3dc9451d,0xbc9c412e,0x4bfb4be5,0xcb6fcbeb,0xc5ebc099,0x4bc54c00,0x43a20000,0xc87fc593,0x4a9e4b80,
0x4a004b17,0x494a476a,0xcb0dc9f2,0x4790495b,0x45bc4891,0x4b784a92,0xcc00cbc0,0x317f43f7,0xbf594004,0x4bf24bf0,0xcb21cbca,0xc742c34c,
0x4bc24c00,0x43d30000,0xc8dbc64e,0x4a5c4b5a,0x49e74b0b,0x49664796,0xcb4aca43,0x469948fb,0x45464867,0x4b8e4aae,0xcbfbcbe0,0xbc6a41aa,
0xc1093db0,0x4be64bf8,0xcac4cb9b,0xc845c4f9,0x4bbf4c00,0x44020000,0xc933c705,0x4a154b30,0x49cd4aff,0x498247c2,0xcb7fca8e,0x45994896,
0x44cf483d,0x4ba14ac9,0xcbe9cbf5,0xc0be3eaa,0xc2633aac,0x4bd74bfd,0xca58cb5d,0xc8e0c642,0x4bbc4c00,0x441a0000,0xc986c7b7,0x49c94b02,
0x49b34af3,0x499d47ee,0xcbabcad3,0x4493482d,0x44574812,0x4bb34ae3,0xcbcbcbff,0xc34037da,0xc3ba33db,0x4bc34c00,0xc9dfcb11,0xc970c780,
0x4bb84c00,0x44320000,0xc9d6c832,0x49794ad0,0x49994ae6,0x49b8480d,0xcbcecb11,0x430f4780,0x43ba47cd,0x4bc34afc,0xcb9fcbfe,0xc4dbb97f,
0xc487b57f,0x4bac4c00,0xc958cab8,0xc9f4c858,0x4bb54c00,0x444b0000,0xca21c887,0x49244a99,0x497d4ad9,0x49d24822,0xcbe7cb49,0x40f0469e,
0x42c64775,0x4bd24b14,0xcb68cbf2,0xc60ebf72,0xc52fbb75,0x4b924bfd,0xc8c7ca52,0xca6bc8e7,0x4bb24c00,0x44630000,0xca67c8d8,0x48cc4a5e,
0x49624acc,0x49eb4838,0xcbf8cb79,0x3d9745b6,0x41cf471b,0x4bde4b2b,0xcb24cbdb,0xc737c20d,0xc5d4be14,0x4b734bf7,0xc82ac9e1,0xcad5c96d,
0x4bae4c00,0x447b0000,0xcaa9c927,0x486f4a1f,0x49464abf,0x4a04484d,0xcc00cba2,0x351b44c9,0x40d746c1,0x4be84b41,0xcad5cbb9,0xc82ac42c,
0xc676c036,0x4b524bee,0xc70ac964,0xcb2fc9e9,0x4bab4c00,0x44930000,0xcae5c972,0x480f49dc,0x49294ab1,0x4a1d4862,0xcbfecbc4,0xba1643ae,
0x3fbd4665,0x4bf14b55,0xca7acb8c,0xc8b2c54c,0xc715c160,0x4b2c4be3,0xc5b1c8dd,0xcb7aca5a,0x4ba74c00,0x44ab0000,0xcb1bc9ba,0x47594996,
0x490c4aa3,0x4a354877,0xcbf2cbdf,0xbf5941c3,0x3dc94608,0x4bf84b69,0xca15cb55,0xc933c665,0xc7b2c288,0x4b044bd5,0xc44bc84d,0xcbb5cabf,
0x4ba34c00,0x44c30000,0xcb4cc9fe,0x468d494d,0x48ee4a95,0x4a4d488c,0xcbdecbf1,0xc1cf3fa4,0x3ba745ab,0x4bfc4b7b,0xc9a6cb14,0xc9aac775,
0xc825c3ae,0x4ad84bc4,0xc1b6c76a,0xcbdfcb17,0x4b9f4c00,0x44db0000,0xcb78ca3f,0x45bc4900,0x48d14a87,0x4a6448a0,0xcbc0cbfd,0xc3eb3b75,
0x3776454c,0x4bff4b8c,0xc92ecac9,0xca19c83d,0xc86fc469,0x4aa94bb1,0xbd97c62b,0xcbf8cb62,0x4b9c4c00,0x44f30000,0xcb9eca7c,0x44e748b0,
0x48b24a78,0x4a7a48b5,0xcb9acc00,0xc4ffaa48,0xa64844ed,0x4c004b9d,0xc8adca74,0xca7ec8ba,0xc8b7c4f9,0x4a764b9b,0x2cb6c4e1,0xcc00cb9e,
0x4b984c00,0x450b0000,0xcbbdcab5,0x440e485d,0x48944a69,0x4a9048c9,0xcb6acbfc,0xc602bc1f,0xb81f448d,0x4bff4bab,0xc825ca17,0xcad8c930,
0xc8fdc587,0x4a414b82,0x3e2dc31b,0xcbf6cbcd,0x4b944c00,0x45230000,0xcbd7cae9,0x42634807,0x48744a5a,0x4aa548dd,0xcb32cbf0,0xc6ffc004,
0xbc06442c,0x4bfc4bb9,0xc72cc9b1,0xcb27c99f,0xc941c614,0x4a094b67,0x4201c067,0xcbdccbed,0x4b904c00,0x453a0000,0xcbeacb1a,0x40a6475e,
0x48554a4b,0x4aba48f1,0xcaf1cbdc,0xc7f3c1f4,0xbdfb4396,0x4bf74bc6,0xc602c943,0xcb6aca07,0xc982c69e,0x49cd4b49,0x446fbaac,0xcbb0cbfd,
0x4b8b4c00,0x45520000,0xcbf8cb46,0x3dc946aa,0x48354a3b,0x4ace4905,0xcaa9cbc1,0xc86fc3df,0xbfef42d2,0x4bf04bd1,0xc4cfc8ce,0xcba1ca65,
0xc9c0c726,0x49904b28,0x45d43852,0xcb73cbff,0x4b874c00,0x456a0000,0xcbffcb6e,0x388445f1,0x48154a2b,0x4ae14918,0xca58cb9e,0xc8e0c4e1,
0xc0f0420d,0x4be74bdb,0xc328c852,0xcbcccabc,0xc9fcc7ac,0x494f4b05,0x472c3fa4,0xcb27cbf1,0x4b834c00,0x45810000,0xcc00cb91,0xb51b4534,
0x47e84a1b,0x4af4492b,0xca00cb74,0xc94ac5ce,0xc1e84147,0x4bdd4be4,0xc0a6c7a1,0xcbeacb08,0xca35c817,0x490c4ae0,0x483a4288,0xcacbcbd5,
0x4b7f4c00,0x45990000,0xcbfacbaf,0xbcce4475,0x47a64a0b,0x4b07493e,0xc9a1cb43,0xc9afc6b5,0xc2de4080,0x4bd04bec,0xbc38c693,0xcbfccb4b,
0xca6bc858,0x48c74ab8,0x48d64499,0xca60cbaa,0x4b7a4c00,0x45b10000,0xcbefcbc9,0xc0294365,0x476449fa,0x4b184951,0xc93ccb0b,0xca0dc796,
0xc3d33f72,0x4bc24bf2,0x3311c57c,0xcc00cb84,0xca9ec896,0x487f4a8e,0x496645e5,0xc9e7cb70,0x4b764c00,0x45c80000,0xcbddcbdd,0xc1e841db,
0x472149e9,0x4b2a4964,0xc8d1cacc,0xca64c838,0xc4633de2,0x4bb24bf7,0x3dfbc45d,0xcbf7cbb2,0xcacec8d3,0x48354a62,0x49eb4726,0xc962cb28,
0x4b714c00,0x45df0000,0xcbc5cbed,0xc3a2404e,0x46dd49d8,0x4b3a4976,0xc85fca87,0xcab3c8a0,0xc4db3c51,0x4b9f4bfb,0x4185c26f,0xcbe1cbd6,
0xcafbc90e,0x47d24a33,0x4a64482d,0xc8d1cad3,0x4b6c4c00,0x45f70000,0xcba7cbf8,0xc4ab3d7e,0x469949c7,0x4b4a4989,0xc7d2ca3b,0xcafbc905,
0xc552397f,0x4b8b4bfe,0x4402c01d,0xcbbfcbef,0xcb24c948,0x47374a02,0x4ace48bf,0xc835ca71,0x4b684c00,0x460e0000,0xcb83cbff,0xc58138b6,
0x465449b5,0x4b59499b,0xc6ddc9e9,0xcb3ac964,0xc5c834b6,0x4b764c00,0x453abb11,0xcb90cbfd,0xcb4ac980,0x469949d0,0x4b2a4948,0xc721ca02,
0x2c002c00,0x2c002c00,0x2c002c00,0x2c002c00,0x2b642c00,0x261f29a8,0xa61f0000,0xab64a9a8,0x29a82c00,0xa9a80000,0xa9a8ac00,0x29a80000,
0x261f2c00,0xab64a9a8,0x2b640000,0xa61f29a8,0x2c00,0xac00,0x2c00,0xac00,0xa61f2c00,0x2b64a9a8,0xab640000,0x261f29a8,
0xa9a82c00,0x29a80000,0x29a8ac00,0xa9a80000,0xab642c00,0xa61f29a8,0x261f0000,0x2b64a9a8,0,0,0,0,
0x261f0000,0x2b6429a8,0x2b642c00,0x261f29a8,0x29a80000,0x29a82c00,0xa9a80000,0xa9a8ac00,0x2b640000,0xa61f29a8,0xa61fac00,0x2b6429a8,
0x2c000000,0xac000000,0x2c000000,0xac000000,0x2b640000,0xa61fa9a8,0xa61f2c00,0x2b64a9a8,0x29a80000,0x29a8ac00,0xa9a80000,0xa9a82c00,
0x261f0000,0x2b64a9a8,0x2b64ac00,0x261fa9a8,0xac002c00,0xac002c00,0xac002c00,0xac002c00,0xab642c00,0xa61f29a8,0x261f0000,0x2b64a9a8,
0xa9a82c00,0x29a80000,0x29a8ac00,0xa9a80000,0xa61f2c00,0x2b64a9a8,0xab640000,0x261f29a8,0x2c00,0xac00,0x2c00,0xac00,
0x261f2c00,0xab64a9a8,0x2b640000,0xa61f29a8,0x29a82c00,0xa9a80000,0xa9a8ac00,0x29a80000,0x2b642c00,0x261f29a8,0xa61f0000,0xab64a9a8,
0,0,0,0,0xa61f0000,0xab6429a8,0xab642c00,0xa61f29a8,0xa9a80000,0xa9a82c00,0x29a80000,0x29a8ac00,
0xab640000,0x261f29a8,0x261fac00,0xab6429a8,0xac000000,0x2c000000,0xac000000,0x2c000000,0xab640000,0x261fa9a8,0x261f2c00,0xab64a9a8,
0xa9a80000,0xa9a8ac00,0x29a80000,0x29a82c00,0xa61f0000,0xab64a9a8,0xab64ac00,0xa61fa9a8,0,0,0,0,
0xa61f0000,0xab64a9a8,0xab64ac00,0xa61fa9a8,0xa9a80000,0xa9a8ac00,0x29a80000,0x29a82c00,0xab640000,0x261fa9a8,0x261f2c00,0xab64a9a8,
0xac000000,0x2c000000,0xac000000,0x2c000000,0xab640000,0x261f29a8,0x261fac00,0xab6429a8,0xa9a80000,0xa9a82c00,0x29a80000,0x29a8ac00,
0xa61f0000,0xab6429a8,0xab642c00,0xa61f29a8,0x2c002c00,0x2c002c00,0x2c002c00,0x2c002c00,0x2b642c00,0x261f29a8,0xa61f0000,0xab64a9a8,
0x29a82c00,0xa9a80000,0xa9a8ac00,0x29a80000,0x261f2c00,0xab64a9a8,0x2b640000,0xa61f29a8,0x2c00,0xac00,0x2c00,0xac00,
0xa61f2c00,0x2b64a9a8,0xab640000,0x261f29a8,0xa9a82c00,0x29a80000,0x29a8ac00,0xa9a80000,0xab642c00,0xa61f29a8,0x261f0000,0x2b64a9a8,
0,0,0,0,0x261f0000,0x2b64a9a8,0x2b64ac00,0x261fa9a8,0x29a80000,0x29a8ac00,0xa9a80000,0xa9a82c00,
0x2b640000,0xa61fa9a8,0xa61f2c00,0x2b64a9a8,0x2c000000,0xac000000,0x2c000000,0xac000000,0x2b640000,0xa61f29a8,0xa61fac00,0x2b6429a8,
0x29a80000,0x29a82c00,0xa9a80000,0xa9a8ac00,0x261f0000,0x2b6429a8,0x2b642c00,0x261f29a8,0xac002c00,0xac002c00,0xac002c00,0xac002c00,
0xab642c00,0xa61f29a8,0x261f0000,0x2b64a9a8,0xa9a82c00,0x29a80000,0x29a8ac00,0xa9a80000,0xa61f2c00,0x2b64a9a8,0xab640000,0x261f29a8,
0x2c00,0xac00,0x2c00,0xac00,0x261f2c00,0xab64a9a8,0x2b640000,0xa61f29a8,0x29a82c00,0xa9a80000,0xa9a8ac00,0x29a80000,
0x2b642c00,0x261f29a8,0xa61f0000,0xab64a9a8,0x2c002c00,0x2c002c00,0x2c002c00,0x2c002c00,0xab64ac00,0xa61fa9a8,0x261f0000,0x2b6429a8,
0x29a82c00,0xa9a80000,0xa9a8ac00,0x29a80000,0xa61fac00,0x2b6429a8,0xab640000,0x261fa9a8,0x2c00,0xac00,0x2c00,0xac00,
0x261fac00,0xab6429a8,0x2b640000,0xa61fa9a8,0xa9a82c00,0x29a80000,0x29a8ac00,0xa9a80000,0x2b64ac00,0x261fa9a8,0xa61f0000,0xab6429a8,
0,0,0,0,0xa61f0000,0xab64a9a8,0xab64ac00,0xa61fa9a8,0x29a80000,0x29a82c00,0xa9a80000,0xa9a8ac00,
0xab640000,0x261fa9a8,0x261f2c00,0xab64a9a8,0x2c000000,0xac000000,0x2c000000,0xac000000,0xab640000,0x261f29a8,0x261fac00,0xab6429a8,
0x29a80000,0x29a8ac00,0xa9a80000,0xa9a82c00,0xa61f0000,0xab6429a8,0xab642c00,0xa61f29a8,0xac002c00,0xac002c00,0xac002c00,0xac002c00,
0x2b64ac00,0x261fa9a8,0xa61f0000,0xab6429a8,0xa9a82c00,0x29a80000,0x29a8ac00,0xa9a80000,0x261fac00,0xab6429a8,0x2b640000,0xa61fa9a8,
0x2c00,0xac00,0x2c00,0xac00,0xa61fac00,0x2b6429a8,0xab640000,0x261fa9a8,0x29a82c00,0xa9a80000,0xa9a8ac00,0x29a80000,
0xab64ac00,0xa61fa9a8,0x261f0000,0x2b6429a8,0,0,0,0,0x261f0000,0x2b64a9a8,0x2b64ac00,0x261fa9a8,
0xa9a80000,0xa9a82c00,0x29a80000,0x29a8ac00,0x2b640000,0xa61fa9a8,0xa61f2c00,0x2b64a9a8,0xac000000,0x2c000000,0xac000000,0x2c000000,
0x2b640000,0xa61f29a8,0xa61fac00,0x2b6429a8,0xa9a80000,0xa9a8ac00,0x29a80000,0x29a82c00,0x261f0000,0x2b6429a8,0x2b642c00,0x261f29a8,
0,0,0,0,0x261f0000,0x2b6429a8,0x2b642c00,0x261f29a8,0xa9a80000,0xa9a8ac00,0x29a80000,0x29a82c00,
0x2b640000,0xa61f29a8,0xa61fac00,0x2b6429a8,0xac000000,0x2c000000,0xac000000,0x2c000000,0x2b640000,0xa61fa9a8,0xa61f2c00,0x2b64a9a8,
0xa9a80000,0xa9a82c00,0x29a80000,0x29a8ac00,0x261f0000,0x2b64a9a8,0x2b64ac00,0x261fa9a8,0x2c002c00,0x2c002c00,0x2c002c00,0x2c002c00,
0xab64ac00,0xa61fa9a8,0x261f0000,0x2b6429a8,0x29a82c00,0xa9a80000,0xa9a8ac00,0x29a80000,0xa61fac00,0x2b6429a8,0xab640000,0x261fa9a8,
0x2c00,0xac00,0x2c00,0xac00,0x261fac00,0xab6429a8,0x2b640000,0xa61fa9a8,0xa9a82c00,0x29a80000,0x29a8ac00,0xa9a80000,
0x2b64ac00,0x261fa9a8,0xa61f0000,0xab6429a8,0,0,0,0,0xa61f0000,0xab6429a8,0xab642c00,0xa61f29a8,
0x29a80000,0x29a8ac00,0xa9a80000,0xa9a82c00,0xab640000,0x261f29a8,0x261fac00,0xab6429a8,0x2c000000,0xac000000,0x2c000000,0xac000000,
0xab640000,0x261fa9a8,0x261f2c00,0xab64a9a8,0x29a80000,0x29a82c00,0xa9a80000,0xa9a8ac00,0xa61f0000,0xab64a9a8,0xab64ac00,0xa61fa9a8,
0xac002c00,0xac002c00,0xac002c00,0xac002c00,0x2b64ac00,0x261fa9a8,0xa61f0000,0xab6429a8,0xa9a82c00,0x29a80000,0x29a8ac00,0xa9a80000,
0x261fac00,0xab6429a8,0x2b640000,0xa61fa9a8,0x2c00,0xac00,0x2c00,0xac00,0xa61fac00,0x2b6429a8,0xab640000,0x261fa9a8,
0x29a82c00,0xa9a80000,0xa9a8ac00,0x29a80000,0xab64ac00,0xa61fa9a8,0x261f0000,0x2b6429a8,0x2bd92c00,0x2aa72b64,0x287229a8,0x223e261f,
0x2aa72c00,0xa23e261f,0xabd9a9a8,0xa872ab64,0x28722c00,0xabd9a61f,0x223ea9a8,0x2aa72b64,0x223e2c00,0xa872ab64,0x2aa729a8,0xabd9a61f,
0xa23e2c00,0x2872ab64,0xaaa729a8,0x2bd9a61f,0xa8722c00,0x2bd9a61f,0xa23ea9a8,0xaaa72b64,0xaaa72c00,0x223e261f,0x2bd9a9a8,0x2872ab64,
0xabd92c00,0xaaa72b64,0xa87229a8,0xa23e261f,0x223e0000,0x2872261f,0x2aa729a8,0x2bd92b64,0x28720000,0x2bd92b64,0x223e29a8,0xaaa7a61f,
0x2aa70000,0x223e2b64,0xabd9a9a8,0x2872a61f,0x2bd90000,0xaaa7261f,0x2872a9a8,0xa23e2b64,0x2bd90000,0xaaa7a61f,0x287229a8,0xa23eab64,
0x2aa70000,0x223eab64,0xabd929a8,0x2872261f,0x28720000,0x2bd9ab64,0x223ea9a8,0xaaa7261f,0x223e0000,0x2872a61f,0x2aa7a9a8,0x2bd9ab64,
0xabd92c00,0xaaa72b64,0xa87229a8,0xa23e261f,0xaaa72c00,0x223e261f,0x2bd9a9a8,0x2872ab64,0xa8722c00,0x2bd9a61f,0xa23ea9a8,0xaaa72b64,
0xa23e2c00,0x2872ab64,0xaaa729a8,0x2bd9a61f,0x223e2c00,0xa872ab64,0x2aa729a8,0xabd9a61f,0x28722c00,0xabd9a61f,0x223ea9a8,0x2aa72b64,
0x2aa72c00,0xa23e261f,0xabd9a9a8,0xa872ab64,0x2bd92c00,0x2aa72b64,0x287229a8,0x223e261f,0xa23e0000,0xa872261f,0xaaa729a8,0xabd92b64,
0xa8720000,0xabd92b64,0xa23e29a8,0x2aa7a61f,0xaaa70000,0xa23e2b64,0x2bd9a9a8,0xa872a61f,0xabd90000,0x2aa7261f,0xa872a9a8,0x223e2b64,
0xabd90000,0x2aa7a61f,0xa87229a8,0x223eab64,0xaaa70000,0xa23eab64,0x2bd929a8,0xa872261f,0xa8720000,0xabd9ab64,0xa23ea9a8,0x2aa7261f,
0xa23e0000,0xa872a61f,0xaaa7a9a8,0xabd9ab64,0xa23e0000,0xa872a61f,0xaaa7a9a8,0xabd9ab64,0xa8720000,0xabd9ab64,0xa23ea9a8,0x2aa7261f,
0xaaa70000,0xa23eab64,0x2bd929a8,0xa872261f,0xabd90000,0x2aa7a61f,0xa87229a8,0x223eab64,0xabd90000,0x2aa7261f,0xa872a9a8,0x223e2b64,
0xaaa70000,0xa23e2b64,0x2bd9a9a8,0xa872a61f,0xa8720000,0xabd92b64,0xa23e29a8,0x2aa7a61f,0xa23e0000,0xa872261f,0xaaa729a8,0xabd92b64,
0x2bd92c00,0x2aa72b64,0x287229a8,0x223e261f,0x2aa72c00,0xa23e261f,0xabd9a9a8,0xa872ab64,0x28722c00,0xabd9a61f,0x223ea9a8,0x2aa72b64,
0x223e2c00,0xa872ab64,0x2aa729a8,0xabd9a61f,0xa23e2c00,0x2872ab64,0xaaa729a8,0x2bd9a61f,0xa8722c00,0x2bd9a61f,0xa23ea9a8,0xaaa72b64,
0xaaa72c00,0x223e261f,0x2bd9a9a8,0x2872ab64,0xabd92c00,0xaaa72b64,0xa87229a8,0xa23e261f,0x223e0000,0x2872a61f,0x2aa7a9a8,0x2bd9ab64,
0x28720000,0x2bd9ab64,0x223ea9a8,0xaaa7261f,0x2aa70000,0x223eab64,0xabd929a8,0x2872261f,0x2bd90000,0xaaa7a61f,0x287229a8,0xa23eab64,
0x2bd90000,0xaaa7261f,0x2872a9a8,0xa23e2b64,0x2aa70000,0x223e2b64,0xabd9a9a8,0x2872a61f,0x28720000,0x2bd92b64,0x223e29a8,0xaaa7a61f,
0x223e0000,0x2872261f,0x2aa729a8,0x2bd92b64,0xabd92c00,0xaaa72b64,0xa87229a8,0xa23e261f,0xaaa72c00,0x223e261f,0x2bd9a9a8,0x2872ab64,
0xa8722c00,0x2bd9a61f,0xa23ea9a8,0xaaa72b64,0xa23e2c00,0x2872ab64,0xaaa729a8,0x2bd9a61f,0x223e2c00,0xa872ab64,0x2aa729a8,0xabd9a61f,
0x28722c00,0xabd9a61f,0x223ea9a8,0x2aa72b64,0x2aa72c00,0xa23e261f,0xabd9a9a8,0xa872ab64,0x2bd92c00,0x2aa72b64,0x287229a8,0x223e261f,
0xa23e0000,0xa872a61f,0xaaa7a9a8,0xabd9ab64,0x28720000,0x2bd92b64,0x223e29a8,0xaaa7a61f,0xaaa70000,0xa23eab64,0x2bd929a8,0xa872261f,
0x2bd90000,0xaaa7261f,0x2872a9a8,0xa23e2b64,0xabd90000,0x2aa7261f,0xa872a9a8,0x223e2b64,0x2aa70000,0x223eab64,0xabd929a8,0x2872261f,
0xa8720000,0xabd92b64,0xa23e29a8,0x2aa7a61f,0x223e0000,0x2872a61f,0x2aa7a9a8,0x2bd9ab64,0x2bd92c00,0x2aa72b64,0x287229a8,0x223e261f,
0xaaa7ac00,0x223ea61f,0x2bd929a8,0x28722b64,0x28722c00,0xabd9a61f,0x223ea9a8,0x2aa72b64,0xa23eac00,0x28722b64,0xaaa7a9a8,0x2bd9261f,
0xa23e2c00,0x2872ab64,0xaaa729a8,0x2bd9a61f,0x2872ac00,0xabd9261f,0x223e29a8,0x2aa7ab64,0xaaa72c00,0x223e261f,0x2bd9a9a8,0x2872ab64,
0x2bd9ac00,0x2aa7ab64,0x2872a9a8,0x223ea61f,0x223e0000,0x2872a61f,0x2aa7a9a8,0x2bd9ab64,0xa8720000,0xabd92b64,0xa23e29a8,0x2aa7a61f,
0x2aa70000,0x223eab64,0xabd929a8,0x2872261f,0xabd90000,0x2aa7261f,0xa872a9a8,0x223e2b64,0x2bd90000,0xaaa7261f,0x2872a9a8,0xa23e2b64,
0xaaa70000,0xa23eab64,0x2bd929a8,0xa872261f,0x28720000,0x2bd92b64,0x223e29a8,0xaaa7a61f,0xa23e0000,0xa872a61f,0xaaa7a9a8,0xabd9ab64,
0xabd92c00,0xaaa72b64,0xa87229a8,0xa23e261f,0x2aa7ac00,0xa23ea61f,0xabd929a8,0xa8722b64,0xa8722c00,0x2bd9a61f,0xa23ea9a8,0xaaa72b64,
0x223eac00,0xa8722b64,0x2aa7a9a8,0xabd9261f,0x223e2c00,0xa872ab64,0x2aa729a8,0xabd9a61f,0xa872ac00,0x2bd9261f,0xa23e29a8,0xaaa7ab64,
0x2aa72c00,0xa23e261f,0xabd9a9a8,0xa872ab64,0xabd9ac00,0xaaa7ab64,0xa872a9a8,0xa23ea61f,0xabd9ac00,0xaaa7ab64,0xa872a9a8,0xa23ea61f,
0x2aa72c00,0xa23e261f,0xabd9a9a8,0xa872ab64,0xa872ac00,0x2bd9261f,0xa23e29a8,0xaaa7ab64,0x223e2c00,0xa872ab64,0x2aa729a8,0xabd9a61f,
0x223eac00,0xa8722b64,0x2aa7a9a8,0xabd9261f,0xa8722c00,0x2bd9a61f,0xa23ea9a8,0xaaa72b64,0x2aa7ac00,0xa23ea61f,0xabd929a8,0xa8722b64,
0xabd92c00,0xaaa72b64,0xa87229a8,0xa23e261f,0xa23e0000,0xa872a61f,0xaaa7a9a8,0xabd9ab64,0x28720000,0x2bd92b64,0x223e29a8,0xaaa7a61f,
0xaaa70000,0xa23eab64,0x2bd929a8,0xa872261f,0x2bd90000,0xaaa7261f,0x2872a9a8,0xa23e2b64,0xabd90000,0x2aa7261f,0xa872a9a8,0x223e2b64,
0x2aa70000,0x223eab64,0xabd929a8,0x2872261f,0xa8720000,0xabd92b64,0xa23e29a8,0x2aa7a61f,0x223e0000,0x2872a61f,0x2aa7a9a8,0x2bd9ab64,
0x2bd9ac00,0x2aa7ab64,0x2872a9a8,0x223ea61f,0xaaa72c00,0x223e261f,0x2bd9a9a8,0x2872ab64,0x2872ac00,0xabd9261f,0x223e29a8,0x2aa7ab64,
0xa23e2c00,0x2872ab64,0xaaa729a8,0x2bd9a61f,0xa23eac00,0x28722b64,0xaaa7a9a8,0x2bd9261f,0x28722c00,0xabd9a61f,0x223ea9a8,0x2aa72b64,
0xaaa7ac00,0x223ea61f,0x2bd929a8,0x28722b64,0x2bd92c00,0x2aa72b64,0x287229a8,0x223e261f,0x223e0000,0x2872a61f,0x2aa7a9a8,0x2bd9ab64,
0xa8720000,0xabd92b64,0xa23e29a8,0x2aa7a61f,0x2aa70000,0x223eab64,0xabd929a8,0x2872261f,0xabd90000,0x2aa7261f,0xa872a9a8,0x223e2b64,
0x2bd90000,0xaaa7261f,0x2872a9a8,0xa23e2b64,0xaaa70000,0xa23eab64,0x2bd929a8,0xa872261f,0x28720000,0x2bd92b64,0x223e29a8,0xaaa7a61f,
0xa23e0000,0xa872a61f,0xaaa7a9a8,0xabd9ab64,0x27fe2800,0x96480000,0x273b2764,0xa2d7a21f,0x27ea27f6,0x9cb29a46,0x26dd270e,0xa41da38b,
0x27c327d9,0x9fc69e3e,0x266d26a7,0xa4c4a472,0x278827a8,0xa164a0a5,0x25ed262f,0xa55fa513,0x27c32800,0x9fc60000,0xa4c4a21f,0xa66da764,
0x25ed270e,0xa55fa38b,0xa73ba62f,0xa2d7a513,0x21642472,0xa788a6a7,0xa7fea7d9,0x16489e3e,0x9cb21a46,0xa7eaa7f6,0xa6dda7a8,0x241d20a5,
0x273b2800,0xa2d70000,0xa55fa764,0x25ed221f,0x1fc62513,0xa7c3a62f,0x1cb2a0a5,0x27ea27a8,0xa4c49e3e,0xa66da7d9,0x26dd2472,0x241d26a7,
0xa7fea70e,0x9648a38b,0x278827f6,0xa1641a46,0x266d2800,0xa4c40000,0x26dd221f,0x241d2764,0xa16420a5,0xa788a7a8,0x25ed27f6,0xa55f9a46,
0xa7fea6a7,0x1648a472,0xa2d71e3e,0xa73ba7d9,0x9fc6a62f,0x27c32513,0xa7eaa70e,0x1cb2a38b,0x255f2800,0xa5ed0000,0x21642764,0xa788a21f,
0xa66d9a46,0xa4c4a7f6,0xa7c3a38b,0x9fc6a70e,0xa41da7d9,0x26dd1e3e,0x9cb2a6a7,0x27ea2472,0x273b20a5,0x22d727a8,0x27fe2513,0x1648262f,
0x241d2800,0xa6dd0000,0xa7eaa21f,0x9cb2a764,0xa7fea38b,0x9648a70e,0x2164a513,0x2788262f,0x22d7a472,0x273b26a7,0x255f27d9,0xa5ed1e3e,
0x24c427f6,0xa66d1a46,0xa7c3a0a5,0x9fc6a7a8,0x21642800,0xa7880000,0x1648a764,0x27fe221f,0xa6dda62f,0x241da513,0x24c427a8,0xa66d20a5,
0x27ea1e3e,0x1cb227d9,0xa7c3a472,0x1fc6a6a7,0xa55f238b,0xa5eda70e,0x273b9a46,0x22d727f6,0x1cb22800,0xa7ea0000,0x27c3221f,0x9fc62764,
0xa2d7a7a8,0x273ba0a5,0xa7fe9a46,0x9648a7f6,0x255f26a7,0xa5ed2472,0x27889e3e,0x216427d9,0xa6dda513,0x241da62f,0xa66d238b,0xa4c4a70e,
0x96482800,0xa7fe0000,0xa2d72764,0xa73ba21f,0x1cb2a7f6,0x27ea1a46,0x241da70e,0x26dd238b,0x9fc627d9,0xa7c39e3e,0xa4c426a7,0xa66da472,
0x2164a7a8,0x278820a5,0x255fa62f,0x25ed2513,0x9fc62800,0xa7c30000,0xa66da21f,0x24c4a764,0x255fa70e,0x25ed238b,0x22d7262f,0xa73b2513,
0xa7882472,0xa164a6a7,0x1648a7d9,0x27fe9e3e,0x27ea9a46,0x9cb227f6,0xa41d27a8,0xa6dda0a5,0xa2d72800,0xa73b0000,0x25eda764,0x255f221f,
0x27c3a513,0x1fc6262f,0xa7ea20a5,0x1cb2a7a8,0xa66d9e3e,0x24c4a7d9,0x241d2472,0xa6dd26a7,0x1648270e,0xa7fe238b,0x2164a7f6,0x27889a46,
0xa4c42800,0xa66d0000,0x241d221f,0xa6dd2764,0x2788a0a5,0xa16427a8,0x255fa7f6,0x25ed1a46,0x1648a6a7,0x27fea472,0xa73b1e3e,0x22d7a7d9,
0xa7c3262f,0x9fc6a513,0x9cb2270e,0xa7ea238b,0xa5ed2800,0xa55f0000,0xa7882764,0xa164a21f,0x24c41a46,0xa66d27f6,0x1fc6238b,0xa7c3270e,
0x26dda7d9,0x241d1e3e,0x27eaa6a7,0x1cb22472,0xa2d7a0a5,0x273ba7a8,0x9648a513,0x27fea62f,0xa6dd2800,0xa41d0000,0x9cb2a21f,0x27eaa764,
0x1648238b,0xa7fe270e,0xa7882513,0x2164a62f,0x273ba472,0xa2d726a7,0xa5ed27d9,0xa55f1e3e,0x266da7f6,0x24c49a46,0x1fc620a5,0xa7c327a8,
0xa7882800,0xa1640000,0x27fea764,0x9648221f,0xa41d262f,0xa6dd2513,0x266da7a8,0x24c4a0a5,0x1cb21e3e,0xa7ea27d9,0x1fc6a472,0x27c3a6a7,
0x25eda38b,0xa55f270e,0xa2d71a46,0x273ba7f6,0xa7ea2800,0x9cb20000,0x9fc6221f,0xa7c32764,0xa73b27a8,0xa2d720a5,0x16481a46,0xa7fe27f6,
0xa5ed26a7,0xa55f2472,0x21649e3e,0xa78827d9,0xa41d2513,0xa6dd262f,0x24c4a38b,0xa66d270e,0xa7fe2800,0x16480000,0xa73b2764,0x22d7a21f,
0xa7ea27f6,0x1cb29a46,0xa6dd270e,0x241da38b,0xa7c327d9,0x1fc69e3e,0xa66d26a7,0x24c4a472,0xa78827a8,0x2164a0a5,0xa5ed262f,0x255fa513,
0xa7c32800,0x1fc60000,0x24c4a21f,0x266da764,0xa5ed270e,0x255fa38b,0x273ba62f,0x22d7a513,0xa1642472,0x2788a6a7,0x27fea7d9,0x96489e3e,
0x1cb21a46,0x27eaa7f6,0x26dda7a8,0xa41d20a5,0xa73b2800,0x22d70000,0x255fa764,0xa5ed221f,0x9fc62513,0x27c3a62f,0x9cb2a0a5,0xa7ea27a8,
0x24c49e3e,0x266da7d9,0xa6dd2472,0xa41d26a7,0x27fea70e,0x1648a38b,0xa78827f6,0x21641a46,0xa66d2800,0x24c40000,0xa6dd221f,0xa41d2764,
0x216420a5,0x2788a7a8,0xa5ed27f6,0x255f9a46,0x27fea6a7,0x9648a472,0x22d71e3e,0x273ba7d9,0x1fc6a62f,0xa7c32513,0x27eaa70e,0x9cb2a38b,
0xa55f2800,0x25ed0000,0xa1642764,0x2788a21f,0x266d9a46,0x24c4a7f6,0x27c3a38b,0x1fc6a70e,0x241da7d9,0xa6dd1e3e,0x1cb2a6a7,0xa7ea2472,
0xa73b20a5,0xa2d727a8,0xa7fe2513,0x9648262f,0xa41d2800,0x26dd0000,0x27eaa21f,0x1cb2a764,0x27fea38b,0x1648a70e,0xa164a513,0xa788262f,
0xa2d7a472,0xa73b26a7,0xa55f27d9,0x25ed1e3e,0xa4c427f6,0x266d1a46,0x27c3a0a5,0x1fc6a7a8,0xa1642800,0x27880000,0x9648a764,0xa7fe221f,
0x26dda62f,0xa41da513,0xa4c427a8,0x266d20a5,0xa7ea1e3e,0x9cb227d9,0x27c3a472,0x9fc6a6a7,0x255f238b,0x25eda70e,0xa73b9a46,0xa2d727f6,
0x9cb22800,0x27ea0000,0xa7c3221f,0x1fc62764,0x22d7a7a8,0xa73ba0a5,0x27fe9a46,0x1648a7f6,0xa55f26a7,0x25ed2472,0xa7889e3e,0xa16427d9,
0x26dda513,0xa41da62f,0x266d238b,0x24c4a70e,0x16482800,0x27fe0000,0x22d72764,0x273ba21f,0x9cb2a7f6,0xa7ea1a46,0xa41da70e,0xa6dd238b,
0x1fc627d9,0x27c39e3e,0x24c426a7,0x266da472,0xa164a7a8,0xa78820a5,0xa55fa62f,0xa5ed2513,0x1fc62800,0x27c30000,0x266da21f,0xa4c4a764,
0xa55fa70e,0xa5ed238b,0xa2d7262f,0x273b2513,0x27882472,0x2164a6a7,0x9648a7d9,0xa7fe9e3e,0xa7ea9a46,0x1cb227f6,0x241d27a8,0x26dda0a5,
0x22d72800,0x273b0000,0xa5eda764,0xa55f221f,0xa7c3a513,0x9fc6262f,0x27ea20a5,0x9cb2a7a8,0x266d9e3e,0xa4c4a7d9,0xa41d2472,0x26dd26a7,
0x9648270e,0x27fe238b,0xa164a7f6,0xa7889a46,0x24c42800,0x266d0000,0xa41d221f,0x26dd2764,0xa788a0a5,0x216427a8,0xa55fa7f6,0xa5ed1a46,
0x9648a6a7,0xa7fea472,0x273b1e3e,0xa2d7a7d9,0x27c3262f,0x1fc6a513,0x1cb2270e,0x27ea238b,0x25ed2800,0x255f0000,0x27882764,0x2164a21f,
0xa4c41a46,0x266d27f6,0x9fc6238b,0x27c3270e,0xa6dda7d9,0xa41d1e3e,0xa7eaa6a7,0x9cb22472,0x22d7a0a5,0xa73ba7a8,0x1648a513,0xa7fea62f,
0x26dd2800,0x241d0000,0x1cb2a21f,0xa7eaa764,0x9648238b,0x27fe270e,0x27882513,0xa164a62f,0xa73ba472,0x22d726a7,0x25ed27d9,0x255f1e3e,
0xa66da7f6,0xa4c49a46,0x9fc620a5,0x27c327a8,0x27882800,0x21640000,0xa7fea764,0x1648221f,0x241d262f,0x26dd2513,0xa66da7a8,0xa4c4a0a5,
0x9cb21e3e,0x27ea27d9,0x9fc6a472,0xa7c3a6a7,0xa5eda38b,0x255f270e,0x22d71a46,0xa73ba7f6,0x27ea2800,0x1cb20000,0x1fc6221f,0x27c32764,
0x273b27a8,0x22d720a5,0x96481a46,0x27fe27f6,0x25ed26a7,0x255f2472,0xa1649e3e,0x278827d9,0x241d2513,0x26dd262f,0xa4c4a38b,0x266d270e,
0x255f25a8,0xa5eda5a8,0x2164221f,0xa788a764,0x24c42513,0xa66da62f,0x1fc620a5,0xa7c3a7a8,0x241d2472,0xa6dda6a7,0x1cb21e3e,0xa7eaa7d9,
0x22d7238b,0xa73ba70e,0x16481a46,0xa7fea7f6,0xa41da5a8,0x26dd25a8,0x27ea2764,0x1cb2221f,0x9648a0a5,0x27fe27a8,0x278827f6,0xa1649a46,
0x22d71e3e,0x273b27d9,0x255f26a7,0xa5eda472,0x266d2513,0x24c4262f,0x1fc6238b,0xa7c3a70e,0x216425a8,0xa788a5a8,0x1648a21f,0x27fe2764,
0xa41d9a46,0xa6dda7f6,0x266d238b,0x24c4270e,0xa7eaa6a7,0x9cb2a472,0x27c327d9,0x9fc61e3e,0xa5eda7a8,0x255f20a5,0x22d7262f,0xa73ba513,
0x9cb2a5a8,0x27ea25a8,0xa7c3a764,0x1fc6a21f,0x273b238b,0x22d7270e,0x9648a513,0x27fe262f,0x255f27d9,0xa5ed9e3e,0x27882472,0x216426a7,
0xa41d1a46,0xa6dda7f6,0x24c427a8,0xa66da0a5,0x964825a8,0xa7fea5a8,0xa2d7221f,0xa73ba764,0xa7eaa62f,0x1cb2a513,0xa6dda7a8,0x241da0a5,
0x1fc6a472,0x27c326a7,0x24c49e3e,0x266d27d9,0x2788270e,0xa164238b,0x25ed27f6,0xa55f1a46,0x1fc6a5a8,0x27c325a8,0x266d2764,0xa4c4221f,
0x25ed27a8,0xa55f20a5,0xa73b9a46,0xa2d7a7f6,0xa7889e3e,0xa164a7d9,0x1648a6a7,0x27fe2472,0x1cb2a62f,0x27ea2513,0x26dd270e,0xa41d238b,
0xa2d725a8,0xa73ba5a8,0x25eda21f,0x255f2764,0x9fc6a7f6,0x27c31a46,0x9cb2270e,0xa7eaa38b,0x266d26a7,0xa4c42472,0xa41da7d9,0x26dd9e3e,
0xa7fea0a5,0x9648a7a8,0x27882513,0xa164262f,0x24c4a5a8,0x266d25a8,0xa41da764,0x26dda21f,0xa164270e,0xa788a38b,0x25ed262f,0xa55f2513,
0x1648a7d9,0x27fe1e3e,0xa73ba472,0x22d7a6a7,0x1fc627f6,0xa7c31a46,0x27ea20a5,0x9cb227a8,0xa5ed25a8,0xa55fa5a8,0xa788221f,0xa164a764,
0x266da513,0x24c4262f,0x27c3a0a5,0x1fc627a8,0xa6dd2472,0xa41da6a7,0xa7ea1e3e,0x9cb2a7d9,0x273ba38b,0x22d7270e,0x27fe9a46,0x164827f6,
0x26dda5a8,0x241d25a8,0x1cb22764,0xa7ea221f,0xa7fe20a5,0x9648a7a8,0x2164a7f6,0x27881a46,0x273b1e3e,0xa2d727d9,0xa5ed26a7,0xa55fa472,
0xa4c4a513,0x266da62f,0x27c3a38b,0x1fc6270e,0xa78825a8,0xa164a5a8,0x27fea21f,0x96482764,0x26dd1a46,0xa41d27f6,0xa4c4a38b,0x266da70e,
0x9cb2a6a7,0x27eaa472,0x9fc627d9,0xa7c31e3e,0xa55f27a8,0xa5eda0a5,0x273ba62f,0x22d72513,0x27eaa5a8,0x1cb225a8,0x1fc6a764,0x27c3a21f,
0xa2d7a38b,0x273ba70e,0xa7fe2513,0x9648a62f,0xa5ed27d9,0xa55f9e3e,0x21642472,0xa78826a7,0x26dd9a46,0xa41d27f6,0x266da7a8,0x24c420a5,
0xa7fe25a8,0x1648a5a8,0xa73b221f,0x22d7a764,0x9cb2262f,0xa7ea2513,0xa41d27a8,0xa6dd20a5,0x27c3a472,0x9fc626a7,0x266d9e3e,0xa4c427d9,
0x2164a70e,0x2788a38b,0x255fa7f6,0x25ed9a46,0x27c3a5a8,0x9fc625a8,0xa4c42764,0xa66d221f,0x255fa7a8,0x25eda0a5,0x22d71a46,0xa73b27f6,
0xa1649e3e,0x2788a7d9,0x27fea6a7,0x96482472,0xa7ea262f,0x1cb2a513,0x241da70e,0x26dda38b,0xa73b25a8,0x22d7a5a8,0x255fa21f,0xa5ed2764,
0xa7c327f6,0x9fc69a46,0x27eaa70e,0x9cb2238b,0xa4c426a7,0xa66d2472,0x26dda7d9,0x241d9e3e,0x164820a5,0xa7fe27a8,0x2164a513,0x2788a62f,
0x266da5a8,0xa4c425a8,0x26dda764,0x241da21f,0x2788a70e,0xa164238b,0x255fa62f,0x25eda513,0x27fea7d9,0x96481e3e,0x22d7a472,0x273ba6a7,
0x27c3a7f6,0x1fc69a46,0x1cb2a0a5,0x27eaa7a8,0xa55f25a8,0x25eda5a8,0xa164221f,0x2788a764,0xa4c42513,0x266da62f,0x9fc620a5,0x27c3a7a8,
0xa41d2472,0x26dda6a7,0x9cb21e3e,0x27eaa7d9,0xa2d7238b,0x273ba70e,0x96481a46,0x27fea7f6,0x241da5a8,0xa6dd25a8,0xa7ea2764,0x9cb2221f,
0x1648a0a5,0xa7fe27a8,0xa78827f6,0x21649a46,0xa2d71e3e,0xa73b27d9,0xa55f26a7,0x25eda472,0xa66d2513,0xa4c4262f,0x9fc6238b,0x27c3a70e,
0xa16425a8,0x2788a5a8,0x9648a21f,0xa7fe2764,0x241d9a46,0x26dda7f6,0xa66d238b,0xa4c4270e,0x27eaa6a7,0x1cb2a472,0xa7c327d9,0x1fc61e3e,
0x25eda7a8,0xa55f20a5,0xa2d7262f,0x273ba513,0x1cb2a5a8,0xa7ea25a8,0x27c3a764,0x9fc6a21f,0xa73b238b,0xa2d7270e,0x1648a513,0xa7fe262f,
0xa55f27d9,0x25ed9e3e,0xa7882472,0xa16426a7,0x241d1a46,0x26dda7f6,0xa4c427a8,0x266da0a5,0x164825a8,0x27fea5a8,0x22d7221f,0x273ba764,
0x27eaa62f,0x9cb2a513,0x26dda7a8,0xa41da0a5,0x9fc6a472,0xa7c326a7,0xa4c49e3e,0xa66d27d9,0xa788270e,0x2164238b,0xa5ed27f6,0x255f1a46,
0x9fc6a5a8,0xa7c325a8,0xa66d2764,0x24c4221f,0xa5ed27a8,0x255f20a5,0x273b9a46,0x22d7a7f6,0x27889e3e,0x2164a7d9,0x9648a6a7,0xa7fe2472,
0x9cb2a62f,0xa7ea2513,0xa6dd270e,0x241d238b,0x22d725a8,0x273ba5a8,0xa5eda21f,0xa55f2764,0x1fc6a7f6,0xa7c31a46,0x1cb2270e,0x27eaa38b,
0xa66d26a7,0x24c42472,0x241da7d9,0xa6dd9e3e,0x27fea0a5,0x1648a7a8,0xa7882513,0x2164262f,0xa4c4a5a8,0xa66d25a8,0x241da764,0xa6dda21f,
0x2164270e,0x2788a38b,0xa5ed262f,0x255f2513,0x9648a7d9,0xa7fe1e3e,0x273ba472,0xa2d7a6a7,0x9fc627f6,0x27c31a46,0xa7ea20a5,0x1cb227a8,
0x25ed25a8,0x255fa5a8,0x2788221f,0x2164a764,0xa66da513,0xa4c4262f,0xa7c3a0a5,0x9fc627a8,0x26dd2472,0x241da6a7,0x27ea1e3e,0x1cb2a7d9,
0xa73ba38b,0xa2d7270e,0xa7fe9a46,0x964827f6,0xa6dda5a8,0xa41d25a8,0x9cb22764,0x27ea221f,0x27fe20a5,0x1648a7a8,0xa164a7f6,0xa7881a46,
0xa73b1e3e,0x22d727d9,0x25ed26a7,0x255fa472,0x24c4a513,0xa66da62f,0xa7c3a38b,0x9fc6270e,0x278825a8,0x2164a5a8,0xa7fea21f,0x16482764,
0xa6dd1a46,0x241d27f6,0x24c4a38b,0xa66da70e,0x1cb2a6a7,0xa7eaa472,0x1fc627d9,0x27c31e3e,0x255f27a8,0x25eda0a5,0xa73ba62f,0xa2d72513,
0xa7eaa5a8,0x9cb225a8,0x9fc6a764,0xa7c3a21f,0x22d7a38b,0xa73ba70e,0x27fe2513,0x1648a62f,0x25ed27d9,0x255f9e3e,0xa1642472,0x278826a7,
0xa6dd9a46,0x241d27f6,0xa66da7a8,0xa4c420a5,0x27fe25a8,0x9648a5a8,0x273b221f,0xa2d7a764,0x1cb2262f,0x27ea2513,0x241d27a8,0x26dd20a5,
0xa7c3a472,0x1fc626a7,0xa66d9e3e,0x24c427d9,0xa164a70e,0xa788a38b,0xa55fa7f6,0xa5ed9a46,0xa7c3a5a8,0x1fc625a8,0x24c42764,0x266d221f,
0xa55fa7a8,0xa5eda0a5,0xa2d71a46,0x273b27f6,0x21649e3e,0xa788a7d9,0xa7fea6a7,0x16482472,0x27ea262f,0x9cb2a513,0xa41da70e,0xa6dda38b,
0x273b25a8,0xa2d7a5a8,0xa55fa21f,0x25ed2764,0x27c327f6,0x1fc69a46,0xa7eaa70e,0x1cb2238b,0x24c426a7,0x266d2472,0xa6dda7d9,0xa41d9e3e,
0x964820a5,0x27fe27a8,0xa164a513,0xa788a62f,0xa66da5a8,0x24c425a8,0xa6dda764,0xa41da21f,0xa788a70e,0x2164238b,0xa55fa62f,0xa5eda513,
0xa7fea7d9,0x16481e3e,0xa2d7a472,0xa73ba6a7,0xa7c3a7f6,0x9fc69a46,0x9cb2a0a5,0xa7eaa7a8,
};

#define PROF(slot) do {} while (0)
#define PROF3(slot) do {} while (0)
#define PROF2(slot) do {} while (0)

__device__ __forceinline__ uint32_t smem_u32(const void* p) { return (uint32_t)__cvta_generic_to_shared(p); }

__device__ __forceinline__ void mbar_init(uint32_t a, uint32_t c) {
  asm volatile("mbarrier.init.shared::cta.b64 [%0], %1;\n" ::"r"(a), "r"(c) : "memory");
}
__device__ __forceinline__ void mbar_expect_tx(uint32_t a, uint32_t bytes) {
  asm volatile("mbarrier.arrive.expect_tx.shared::cta.b64 _, [%0], %1;\n" ::"r"(a), "r"(bytes) : "memory");
}
__device__ __forceinline__ void mbar_arrive_cluster(uint32_t cluster_addr) {
  asm volatile("mbarrier.arrive.shared::cluster.b64 _, [%0];\n" ::"r"(cluster_addr) : "memory");
}
__device__ __forceinline__ void mbar_arrive_cluster_n(uint32_t cluster_addr, uint32_t n) {
  asm volatile("mbarrier.arrive.shared::cluster.b64 _, [%0], %1;\n" ::"r"(cluster_addr), "r"(n) : "memory");
}
__device__ __forceinline__ bool mbar_try(uint32_t a, uint32_t parity) {
  uint32_t ok;
  asm volatile("{\n.reg .pred p;\nmbarrier.try_wait.parity.shared::cta.b64 p, [%1], %2;\nselp.u32 %0, 1, 0, p;\n}\n"
               : "=r"(ok) : "r"(a), "r"(parity) : "memory");
  return ok;
}
__device__ __forceinline__ void mbar_wait(uint32_t a, uint32_t parity) {
  if (mbar_try(a, parity)) return;
#pragma unroll 1
  for (int n = 0; n < SPIN_LIMIT; n++)
    if (mbar_try(a, parity)) break;
}
__device__ __forceinline__ bool elect_one() {
  uint32_t p;
  asm volatile("{\n.reg .pred P;\nelect.sync _|P, 0xffffffff;\nselp.u32 %0, 1, 0, P;\n}\n" : "=r"(p));
  return p;
}
__device__ __forceinline__ uint32_t mapa(uint32_t a, uint32_t rank) {
  uint32_t r;
  asm volatile("mapa.shared::cluster.u32 %0, %1, %2;\n" : "=r"(r) : "r"(a), "r"(rank));
  return r;
}
__device__ __forceinline__ void nb_sync(int id, int n) { asm volatile("bar.sync %0, %1;\n" ::"r"(id), "r"(n) : "memory"); }
__device__ __forceinline__ void nb_arrive(int id, int n) { asm volatile("bar.arrive %0, %1;\n" ::"r"(id), "r"(n) : "memory"); }
__device__ __forceinline__ void cluster_sync_all() {
  asm volatile("barrier.cluster.arrive.relaxed.aligned;\nbarrier.cluster.wait.aligned;\n" ::: "memory");
}
__device__ __forceinline__ void fence_async_smem() { asm volatile("fence.proxy.async.shared::cta;\n" ::: "memory"); }
__device__ __forceinline__ void fence_async_all() { asm volatile("fence.proxy.async.global;\n" ::: "memory"); }

__device__ __forceinline__ void tma_load_3d(uint32_t dst, const CUtensorMap* tm, uint32_t bar, int c0, int c1, int c2) {
  asm volatile(
      "cp.async.bulk.tensor.3d.shared::cluster.global.mbarrier::complete_tx::bytes [%0], [%1, {%3, %4, %5}], [%2];\n"
      ::"r"(dst), "l"(tm), "r"(bar), "r"(c0), "r"(c1), "r"(c2) : "memory");
}
__device__ __forceinline__ void tma_load_4d(uint32_t dst, const CUtensorMap* tm, uint32_t bar, int c0, int c1, int c2, int c3) {
  asm volatile(
      "cp.async.bulk.tensor.4d.shared::cluster.global.mbarrier::complete_tx::bytes [%0], [%1, {%3, %4, %5, %6}], [%2];\n"
      ::"r"(dst), "l"(tm), "r"(bar), "r"(c0), "r"(c1), "r"(c2), "r"(c3) : "memory");
}
__device__ __forceinline__ void tma_load_3d_mc(uint32_t dst, const CUtensorMap* tm, uint32_t bar, int c0, int c1, int c2) {
  asm volatile(
      "cp.async.bulk.tensor.3d.shared::cluster.global.mbarrier::complete_tx::bytes.multicast::cluster [%0], [%1, {%3, %4, %5}], [%2], %6;\n"
      ::"r"(dst), "l"(tm), "r"(bar), "r"(c0), "r"(c1), "r"(c2), "h"((uint16_t)3) : "memory");
}
__device__ __forceinline__ void tma_load_5d(uint32_t dst, const CUtensorMap* tm, uint32_t bar, int c0, int c4) {
  asm volatile(
      "cp.async.bulk.tensor.5d.shared::cluster.global.mbarrier::complete_tx::bytes [%0], [%1, {%3, %5, %5, %5, %4}], [%2];\n"
      ::"r"(dst), "l"(tm), "r"(bar), "r"(c0), "r"(c4), "r"(0) : "memory");
}
__device__ __forceinline__ void bulk_load(uint32_t dst, const void* src, uint32_t bytes, uint32_t bar) {
  asm volatile("cp.async.bulk.shared::cluster.global.mbarrier::complete_tx::bytes [%0], [%1], %2, [%3];\n"
               ::"r"(dst), "l"(src), "r"(bytes), "r"(bar) : "memory");
}
__device__ __forceinline__ void bulk_commit() { asm volatile("cp.async.bulk.commit_group;\n" ::: "memory"); }
__device__ __forceinline__ void bulk_wait0() { asm volatile("cp.async.bulk.wait_group 0;\n" ::: "memory"); }
__device__ __forceinline__ void prefetch_tmap(const CUtensorMap* tm) {
  asm volatile("prefetch.tensormap [%0];\n" ::"l"(tm) : "memory");
}

__device__ __forceinline__ void wg_fence() { asm volatile("wgmma.fence.sync.aligned;\n" ::: "memory"); }
__device__ __forceinline__ void wg_commit() { asm volatile("wgmma.commit_group.sync.aligned;\n" ::: "memory"); }
template <int N> __device__ __forceinline__ void wg_wait() {
  asm volatile("wgmma.wait_group.sync.aligned %0;\n" ::"n"(N) : "memory");
}
__device__ __forceinline__ uint64_t mkdesc(uint32_t addr, uint32_t lbo, uint32_t sbo, uint32_t swz) {
  return (uint64_t)((addr & 0x3FFFF) >> 4) | ((uint64_t)(lbo >> 4) << 16) | ((uint64_t)(sbo >> 4) << 32) |
         ((uint64_t)swz << 62);
}

#define R4(d, o) "+f"(d[o + 0]), "+f"(d[o + 1]), "+f"(d[o + 2]), "+f"(d[o + 3])
#define R8(d, o) R4(d, o), R4(d, o + 4)
#define R16(d, o) R8(d, o), R8(d, o + 8)
#define R32(d, o) R16(d, o), R16(d, o + 16)
#define R64(d, o) R32(d, o), R32(d, o + 32)

__device__ __forceinline__ void wgmma_n192(float (&d)[96], uint64_t da, uint64_t db, uint32_t acc) {
  asm volatile(
      "{\n.reg .pred p;\nsetp.ne.u32 p, %98, 0;\n"
      "wgmma.mma_async.sync.aligned.m64n192k16.f32.bf16.bf16 "
      "{%0,%1,%2,%3,%4,%5,%6,%7,%8,%9,%10,%11,%12,%13,%14,%15,%16,%17,%18,%19,%20,%21,%22,%23,%24,%25,%26,%27,%28,%29,%30,%31,"
      "%32,%33,%34,%35,%36,%37,%38,%39,%40,%41,%42,%43,%44,%45,%46,%47,%48,%49,%50,%51,%52,%53,%54,%55,%56,%57,%58,%59,%60,%61,%62,%63,"
      "%64,%65,%66,%67,%68,%69,%70,%71,%72,%73,%74,%75,%76,%77,%78,%79,%80,%81,%82,%83,%84,%85,%86,%87,%88,%89,%90,%91,%92,%93,%94,%95}, "
      "%96, %97, p, 1, 1, 0, 1;\n}\n"
      : R64(d, 0), R32(d, 64)
      : "l"(da), "l"(db), "r"(acc));
}
__device__ __forceinline__ void wgmma_n128(float (&d)[64], uint64_t da, uint64_t db, uint32_t acc) {
  asm volatile(
      "{\n.reg .pred p;\nsetp.ne.u32 p, %66, 0;\n"
      "wgmma.mma_async.sync.aligned.m64n128k16.f32.bf16.bf16 "
      "{%0,%1,%2,%3,%4,%5,%6,%7,%8,%9,%10,%11,%12,%13,%14,%15,%16,%17,%18,%19,%20,%21,%22,%23,%24,%25,%26,%27,%28,%29,%30,%31,"
      "%32,%33,%34,%35,%36,%37,%38,%39,%40,%41,%42,%43,%44,%45,%46,%47,%48,%49,%50,%51,%52,%53,%54,%55,%56,%57,%58,%59,%60,%61,%62,%63}, "
      "%64, %65, p, 1, 1, 0, 1;\n}\n"
      : R64(d, 0)
      : "l"(da), "l"(db), "r"(acc));
}
template <int N> __device__ __forceinline__ void fence_regs(float (&d)[N]) {
#pragma unroll
  for (int i = 0; i < N; i++) asm volatile("" : "+f"(d[i])::"memory");
}

__device__ __forceinline__ void mma16816(float (&d)[4], uint32_t a0, uint32_t a1, uint32_t a2, uint32_t a3, uint32_t b0,
                                         uint32_t b1) {
  asm("mma.sync.aligned.m16n8k16.row.col.f32.bf16.bf16.f32 {%0,%1,%2,%3}, {%4,%5,%6,%7}, {%8,%9}, {%0,%1,%2,%3};\n"
      : "+f"(d[0]), "+f"(d[1]), "+f"(d[2]), "+f"(d[3])
      : "r"(a0), "r"(a1), "r"(a2), "r"(a3), "r"(b0), "r"(b1));
}
__device__ __forceinline__ void mma16816_z(float (&d)[4], uint32_t a0, uint32_t a1, uint32_t a2, uint32_t a3, uint32_t b0,
                                           uint32_t b1) {
  asm("mma.sync.aligned.m16n8k16.row.col.f32.bf16.bf16.f32 {%0,%1,%2,%3}, {%4,%5,%6,%7}, {%8,%9}, {%10,%10,%10,%10};\n"
      : "=f"(d[0]), "=f"(d[1]), "=f"(d[2]), "=f"(d[3])
      : "r"(a0), "r"(a1), "r"(a2), "r"(a3), "r"(b0), "r"(b1), "f"(0.f));
}
__device__ __forceinline__ void ldsm4t(uint32_t (&r)[4], uint32_t a) {
  asm volatile("ldmatrix.sync.aligned.m8n8.x4.trans.shared.b16 {%0,%1,%2,%3}, [%4];\n"
               : "=r"(r[0]), "=r"(r[1]), "=r"(r[2]), "=r"(r[3]) : "r"(a) : "memory");
}
__device__ __forceinline__ void ldsm2t(uint32_t& r0, uint32_t& r1, uint32_t a) {
  asm volatile("ldmatrix.sync.aligned.m8n8.x2.trans.shared.b16 {%0,%1}, [%2];\n" : "=r"(r0), "=r"(r1) : "r"(a) : "memory");
}
__device__ __forceinline__ void st_async128(uint32_t a, uint32_t bar, uint32_t x, uint32_t y, uint32_t z, uint32_t w) {
  asm volatile("st.async.weak.shared::cluster.mbarrier::complete_tx::bytes.v4.b32 [%0], {%2,%3,%4,%5}, [%1];\n"
               ::"r"(a), "r"(bar), "r"(x), "r"(y), "r"(z), "r"(w) : "memory");
}
__device__ __forceinline__ void mbar_arrive(uint32_t a) {
  asm volatile("mbarrier.arrive.shared::cta.b64 _, [%0];\n" ::"r"(a) : "memory");
}
__device__ __forceinline__ void stsm4(uint32_t a, uint32_t r0, uint32_t r1, uint32_t r2, uint32_t r3) {
  asm volatile("stmatrix.sync.aligned.m8n8.x4.shared.b16 [%0], {%1,%2,%3,%4};\n"
               ::"r"(a), "r"(r0), "r"(r1), "r"(r2), "r"(r3) : "memory");
}
__device__ __forceinline__ void stsm4t(uint32_t a, uint32_t r0, uint32_t r1, uint32_t r2, uint32_t r3) {
  asm volatile("stmatrix.sync.aligned.m8n8.x4.trans.shared.b16 [%0], {%1,%2,%3,%4};\n"
               ::"r"(a), "r"(r0), "r"(r1), "r"(r2), "r"(r3) : "memory");
}
__device__ __forceinline__ uint2 lds64(uint32_t a) {
  uint2 v;
  asm volatile("ld.shared.v2.u32 {%0,%1}, [%2];\n" : "=r"(v.x), "=r"(v.y) : "r"(a));
  return v;
}
__device__ __forceinline__ uint4 lds128(uint32_t a) {
  uint4 v;
  asm volatile("ld.shared.v4.u32 {%0,%1,%2,%3}, [%4];\n" : "=r"(v.x), "=r"(v.y), "=r"(v.z), "=r"(v.w) : "r"(a) : "memory");
  return v;
}
__device__ __forceinline__ void sts128(uint32_t a, uint32_t x, uint32_t y, uint32_t z, uint32_t w) {
  asm volatile("st.shared.v4.u32 [%0], {%1,%2,%3,%4};\n" ::"r"(a), "r"(x), "r"(y), "r"(z), "r"(w) : "memory");
}
__device__ __forceinline__ uint32_t pack_bf16(float lo, float hi) {
  uint32_t r;
  asm("cvt.rn.bf16x2.f32 %0, %1, %2;\n" : "=r"(r) : "f"(hi), "f"(lo));
  return r;
}
__device__ __forceinline__ uint32_t bmul2(uint32_t a, uint32_t b) {
  uint32_t r;
  asm("mul.rn.bf16x2 %0, %1, %2;\n" : "=r"(r) : "r"(a), "r"(b));
  return r;
}
__device__ __forceinline__ uint32_t bmax2(uint32_t a, uint32_t b) {
  uint32_t r;
  asm("max.bf16x2 %0, %1, %2;\n" : "=r"(r) : "r"(a), "r"(b));
  return r;
}
__device__ __forceinline__ uint32_t bfma2(uint32_t a, uint32_t b, uint32_t c) {
  uint32_t r;
  asm("fma.rn.bf16x2 %0, %1, %2, %3;\n" : "=r"(r) : "r"(a), "r"(b), "r"(c));
  return r;
}
__device__ __forceinline__ uint32_t badd2(uint32_t a, uint32_t b) {
  uint32_t r;
  asm("add.rn.bf16x2 %0, %1, %2;\n" : "=r"(r) : "r"(a), "r"(b));
  return r;
}
__device__ __forceinline__ void prefetch_l2(const void* p) { asm volatile("prefetch.global.L2 [%0];\n" ::"l"(p)); }
__device__ __forceinline__ void cp_async16n(uint32_t dst, const void* src) {
  asm volatile("cp.async.cg.shared.global [%0], [%1], 16;\n" ::"r"(dst), "l"(src) : "memory");
}
__device__ __forceinline__ void cp_async16(uint32_t dst, const void* src, uint32_t srcbytes) {
  asm volatile("cp.async.cg.shared.global.L2::256B [%0], [%1], 16, %2;\n" ::"r"(dst), "l"(src), "r"(srcbytes) : "memory");
}
__device__ __forceinline__ uint32_t ld_acquire(const uint32_t* p) {
  uint32_t v;
  asm volatile("ld.acquire.gpu.global.u32 %0, [%1];\n" : "=r"(v) : "l"(p) : "memory");
  return v;
}
__device__ __forceinline__ uint32_t ld_relaxed(const uint32_t* p) {
  uint32_t v;
  asm volatile("ld.relaxed.gpu.global.u32 %0, [%1];\n" : "=r"(v) : "l"(p) : "memory");
  return v;
}
__device__ __forceinline__ void st_release(uint32_t* p, uint32_t v) {
  asm volatile("st.release.gpu.global.u32 [%0], %1;\n" ::"l"(p), "r"(v) : "memory");
}
__device__ __forceinline__ void wait_flag(const uint32_t* p, uint32_t want) {
  int n = 0;
  while (ld_relaxed(p) != want && ++n < SPIN_LIMIT) __nanosleep(40);
  (void)ld_acquire(p);
}

struct Params {
  const __nv_bfloat16* x;
  const __nv_bfloat16* w;
  const __nv_bfloat16* q;
  const __nv_bfloat16* k;
  const __nv_bfloat16* v;
  const __nv_bfloat16* shift_k;
  const __nv_bfloat16* ssm_k;
  const __nv_bfloat16* ssm_D;
  const __nv_bfloat16* wo;
  __nv_bfloat16* out;
};

__device__ __forceinline__ uint32_t lds32(uint32_t a) {
  uint32_t v;
  asm volatile("ld.shared.u32 %0, [%1];\n" : "=r"(v) : "r"(a));
  return v;
}
#define W4(d, o) "=f"(d[o + 0]), "=f"(d[o + 1]), "=f"(d[o + 2]), "=f"(d[o + 3])
#define W8(d, o) W4(d, o), W4(d, o + 4)
#define W16(d, o) W8(d, o), W8(d, o + 8)
#define U4(c, d, o) c(d[o + 0]), c(d[o + 1]), c(d[o + 2]), c(d[o + 3])
#define U8(c, d, o) U4(c, d, o), U4(c, d, o + 4)
#define U16(c, d, o) U8(c, d, o), U8(c, d, o + 8)
#define U32(c, d, o) U16(c, d, o), U16(c, d, o + 16)
#define D32 "{%0,%1,%2,%3,%4,%5,%6,%7,%8,%9,%10,%11,%12,%13,%14,%15,%16,%17,%18,%19,%20,%21,%22,%23,%24,%25,%26,%27,%28,%29,%30,%31}"
#define D16 "{%0,%1,%2,%3,%4,%5,%6,%7,%8,%9,%10,%11,%12,%13,%14,%15}"
#define D8 "{%0,%1,%2,%3,%4,%5,%6,%7}"
template <int ACC> __device__ __forceinline__ void hmma_n128t(uint32_t (&d)[32], const uint32_t (&a)[4], uint64_t db) {
  if (ACC)
    asm volatile("wgmma.mma_async.sync.aligned.m64n128k16.f16.f16.f16 " D32 ", {%32,%33,%34,%35}, %36, 1, 1, 1, 1;\n"
                 : U32("+r", d, 0) : "r"(a[0]), "r"(a[1]), "r"(a[2]), "r"(a[3]), "l"(db));
  else
    asm volatile("wgmma.mma_async.sync.aligned.m64n128k16.f16.f16.f16 " D32 ", {%32,%33,%34,%35}, %36, 0, 1, 1, 1;\n"
                 : U32("=r", d, 0) : "r"(a[0]), "r"(a[1]), "r"(a[2]), "r"(a[3]), "l"(db));
}
template <int ACC, int TB> __device__ __forceinline__ void hmma_n32(uint32_t (&d)[8], const uint32_t (&a)[4], uint64_t db) {
  if (ACC)
    asm volatile("wgmma.mma_async.sync.aligned.m64n32k16.f16.f16.f16 " D8 ", {%8,%9,%10,%11}, %12, 1, 1, 1, %13;\n"
                 : U8("+r", d, 0) : "r"(a[0]), "r"(a[1]), "r"(a[2]), "r"(a[3]), "l"(db), "n"(TB));
  else
    asm volatile("wgmma.mma_async.sync.aligned.m64n32k16.f16.f16.f16 " D8 ", {%8,%9,%10,%11}, %12, 0, 1, 1, %13;\n"
                 : U8("=r", d, 0) : "r"(a[0]), "r"(a[1]), "r"(a[2]), "r"(a[3]), "l"(db), "n"(TB));
}
template <int ACC> __device__ __forceinline__ void fmma_n32t(float (&d)[16], const uint32_t (&a)[4], uint64_t db) {
  if (ACC)
    asm volatile("wgmma.mma_async.sync.aligned.m64n32k16.f32.f16.f16 " D16 ", {%16,%17,%18,%19}, %20, 1, 1, 1, 1;\n"
                 : R16(d, 0) : "r"(a[0]), "r"(a[1]), "r"(a[2]), "r"(a[3]), "l"(db));
  else
    asm volatile("wgmma.mma_async.sync.aligned.m64n32k16.f32.f16.f16 " D16 ", {%16,%17,%18,%19}, %20, 0, 1, 1, 1;\n"
                 : W16(d, 0) : "r"(a[0]), "r"(a[1]), "r"(a[2]), "r"(a[3]), "l"(db));
}
template <int N> __device__ __forceinline__ void fence_regs(uint32_t (&d)[N]) {
#pragma unroll
  for (int i = 0; i < N; i++) asm volatile("" : "+r"(d[i])::"memory");
}
__device__ __forceinline__ uint32_t hmul(uint32_t a, uint32_t b) { uint32_t r; asm("mul.rn.f16x2 %0, %1, %2;\n" : "=r"(r) : "r"(a), "r"(b)); return r; }
__device__ __forceinline__ uint32_t hadd(uint32_t a, uint32_t b) { uint32_t r; asm("add.rn.f16x2 %0, %1, %2;\n" : "=r"(r) : "r"(a), "r"(b)); return r; }
__device__ __forceinline__ uint32_t hsub(uint32_t a, uint32_t b) { uint32_t r; asm("sub.rn.f16x2 %0, %1, %2;\n" : "=r"(r) : "r"(a), "r"(b)); return r; }
__device__ __forceinline__ uint32_t hfma(uint32_t a, uint32_t b, uint32_t c) { uint32_t r; asm("fma.rn.f16x2 %0, %1, %2, %3;\n" : "=r"(r) : "r"(a), "r"(b), "r"(c)); return r; }
__device__ __forceinline__ uint32_t hfnma(uint32_t a, uint32_t b, uint32_t c) {
  uint32_t r;
  asm("{\n.reg .b32 t;\nneg.f16x2 t, %1;\nfma.rn.f16x2 %0, t, %2, %3;\n}\n" : "=r"(r) : "r"(a), "r"(b), "r"(c));
  return r;
}
__device__ __forceinline__ uint32_t hrefl(uint32_t p, uint32_t s) {
  uint32_t r;
  asm("{\n.reg .b32 t;\nneg.f16x2 t, %2;\nfma.rn.f16x2 %0, %1, %3, t;\n}\n" : "=r"(r) : "r"(p), "r"(s), "r"(0x40004000u));
  return r;
}
__device__ __forceinline__ void bfly(uint32_t xr, uint32_t xi, uint32_t tr, uint32_t ti, uint32_t yr, uint32_t yi, uint32_t ur,
                                     uint32_t ui, uint32_t& sr, uint32_t& si, uint32_t& dr, uint32_t& di) {
  const uint32_t pr = hfnma(xi, ti, hmul(xr, tr)), pi = hfma(xi, tr, hmul(xr, ti));
  sr = hfnma(yi, ui, hfma(yr, ur, pr));
  si = hfma(yi, ur, hfma(yr, ui, pi));
  dr = hrefl(pr, sr);
  di = hrefl(pi, si);
}
template <int BH> __device__ __forceinline__ void fft_e1(const uint32_t (&d)[32], const uint32_t (&tw)[16], uint32_t (&a2)[2][2][4]) {
#pragma unroll
  for (int be = 0; be < 2; be++)
#pragma unroll
    for (int s = 0; s < 2; s++) {
      const int o = 16 * s + 8 * be + 2 * BH, p = 2 * BH;
      bfly(d[o], d[o + 1], tw[p], tw[p + 1], d[o + 4], d[o + 5], tw[p + 4], tw[p + 5], a2[be][0][s], a2[be][0][2 + s],
           a2[be][1][s], a2[be][1][2 + s]);
    }
}
__device__ __forceinline__ uint32_t hfms(uint32_t a, uint32_t b, uint32_t c) {
  uint32_t r;
  asm("{\n.reg .b32 t;\nneg.f16x2 t, %3;\nfma.rn.f16x2 %0, %1, %2, t;\n}\n" : "=r"(r) : "r"(a), "r"(b), "r"(c));
  return r;
}
template <int C, int J> __device__ __forceinline__ void fft_e2(const uint32_t (&d0)[8], const uint32_t (&d1)[8], uint32_t (&a3)[2][4]) {
  const uint32_t ur = d0[2 * J], ui = d0[4 + 2 * J], hr = d0[2 * J + 1], hi = d0[5 + 2 * J];
  const uint32_t vr = d1[2 * J], vi = d1[4 + 2 * J], gr = d1[2 * J + 1], gi = d1[5 + 2 * J];
  const uint32_t pr = hfnma(ui, hi, hmul(ur, hr)), pi = hfma(ui, hr, hmul(ur, hi));
  a3[0][2 + C] = pr;
  a3[0][C] = pi;
  a3[1][2 + C] = hfnma(vi, hi, hfma(vr, hr, hfnma(ui, gi, hfms(ur, gr, pi))));
  a3[1][C] = hfma(vi, hr, hfma(vr, hi, hfma(ui, gr, hfma(ur, gi, pr))));
}
__device__ __forceinline__ void fft_e3(const uint32_t (&d)[2][8], const uint32_t (&tw)[16], uint32_t zaddr) {
#pragma unroll
  for (int rho = 0; rho < 2; rho++) {
    uint32_t zr[4], zi[4];
#pragma unroll
    for (int nb = 0; nb < 4; nb++) {
      const uint32_t xi = d[nb >> 1][2 * (nb & 1) + rho], xr = d[nb >> 1][4 + 2 * (nb & 1) + rho];
      const uint32_t tr = tw[8 + 4 * rho + 2 * (nb & 1)], ti = tw[9 + 4 * rho + 2 * (nb & 1)];
      zr[nb] = hfnma(xi, ti, hmul(xr, tr));
      zi[nb] = hfma(xi, tr, hmul(xr, ti));
    }
    stsm4(zaddr + rho * 1024, zr[0], zr[1], zr[2], zr[3]);
    stsm4(zaddr + rho * 1024 + 512, zi[0], zi[1], zi[2], zi[3]);
  }
}
__device__ __forceinline__ float bf_lo(uint32_t v) {
  uint32_t r;
  asm("prmt.b32 %0, %1, 0, 0x1044;\n" : "=r"(r) : "r"(v));
  return __uint_as_float(r);
}
__device__ __forceinline__ float bf_hi(uint32_t v) { return __uint_as_float(v & 0xffff0000u); }
__device__ __forceinline__ float ex2(float x) {
  float r;
  asm("ex2.approx.ftz.f32 %0, %1;\n" : "=f"(r) : "f"(x));
  return r;
}
__device__ __forceinline__ float rcp(float x) {
  float r;
  asm("rcp.approx.ftz.f32 %0, %1;\n" : "=f"(r) : "f"(x));
  return r;
}

__device__ __forceinline__ int g2_a(int s) { return ((0xA1054 >> (4 * s)) & 15) * 16384; }
__device__ __forceinline__ int g2_b(int s) { return ((0xCDB32 >> (4 * s)) & 15) * 16384; }
static_assert(OFF_U == 10 * 16384 && OFF_H == 12 * 16384 && OFF_OP == 4 * 16384, "units");
__device__ __forceinline__ int g2_k(int hp, int i) {
  if (i < 2) return hp ^ 1 ^ i;
  if (i == 2 || i == 15) return ((hp & ~1) ^ 2) + (i & 1);
  return ((hp & ~3) + (i < 9 ? 2 * i - 2 : 2 * i - 13)) & 15;
}
__device__ __forceinline__ int y_slot(int wg, int it) {
  static_assert(T_B2 == T_TW + 8192 && T_A1 == T_B2 + 4096, "y slots");
  return OFF_T + T_TW + ((it + 3) & 3) * 4096 + wg * 2048;
}

__device__ __forceinline__ void to_arr(uint32_t (&d)[4], uint4 v) { d[0] = v.x; d[1] = v.y; d[2] = v.z; d[3] = v.w; }

__device__ __forceinline__ void attn_stage(uint32_t sb, int blk, int lane, const float (&acc)[96], uint32_t (&k1)[2][4]) {
  const int lr = lane & 7, lm = lane >> 3;
  const uint32_t base = sb + OFF_VP + (blk * 16 + lr + 8 * (lm & 1)) * 128;
#pragma unroll
  for (int i = 0; i < 8; i++) k1[i >> 2][i & 3] = pack_bf16(acc[34 + 4 * i], acc[35 + 4 * i]);
  const uint32_t kh = sb + OFF_KH + blk * 2048 + lane * 16;
  sts128(kh, k1[0][0], k1[0][1], k1[0][2], k1[0][3]);
  sts128(kh + 512, k1[1][0], k1[1][1], k1[1][2], k1[1][3]);
#pragma unroll
  for (int j = 0; j < 8; j += 2)
    stsm4(base + (((j + (lm >> 1)) ^ lr) << 4), pack_bf16(acc[64 + 4 * j], acc[65 + 4 * j]),
          pack_bf16(acc[66 + 4 * j], acc[67 + 4 * j]), pack_bf16(acc[68 + 4 * j], acc[69 + 4 * j]),
          pack_bf16(acc[70 + 4 * j], acc[71 + 4 * j]));
}
__device__ __forceinline__ void attn_pack(const float (&acc)[96], uint32_t (&qa)[2][8], uint32_t (&k0)[2][4]) {
#pragma unroll
  for (int hd = 0; hd < 2; hd++) {
#pragma unroll
    for (int i = 0; i < 8; i++) {
      asm volatile("cvt.rn.bf16x2.f32 %0, %1, %2;\n" : "=r"(qa[hd][i]) : "f"(acc[16 * hd + 2 * i + 1]), "f"(acc[16 * hd + 2 * i]));
    }
#pragma unroll
    for (int i = 0; i < 4; i++) {
      asm volatile("cvt.rn.bf16x2.f32 %0, %1, %2;\n" : "=r"(k0[hd][i]) : "f"(acc[33 + 16 * hd + 4 * i]), "f"(acc[32 + 16 * hd + 4 * i]));
    }
  }
}
__device__ __forceinline__ void attn_own(const uint32_t (&k0)[2][4], const uint32_t (&k1)[2][4], bool le0, bool le1,
                                         const uint32_t (&qa)[2][8], float (&l)[2][4]) {
#pragma unroll
  for (int hd = 0; hd < 2; hd++) {
    float s0[4], s1[4];
    mma16816_z(s0, qa[hd][0], qa[hd][1], qa[hd][2], qa[hd][3], k0[hd][0], k0[hd][1]);
    mma16816_z(s1, qa[hd][0], qa[hd][1], qa[hd][2], qa[hd][3], k1[hd][0], k1[hd][1]);
    mma16816(s0, qa[hd][4], qa[hd][5], qa[hd][6], qa[hd][7], k0[hd][2], k0[hd][3]);
    mma16816(s1, qa[hd][4], qa[hd][5], qa[hd][6], qa[hd][7], k1[hd][2], k1[hd][3]);
    l[hd][0] = s0[0];
    l[hd][1] = s0[1];
    l[hd][2] = le0 ? s1[2] : s0[2];
    l[hd][3] = le1 ? s1[3] : s0[3];
  }
}
template <int N> __device__ __forceinline__ void quad_softmax(float (&x)[N][2], uint32_t (&pp)[N]) {
  const float c2 = 1.4426950408889634f;
  uint32_t q[N], mx[N / 2];
#pragma unroll
  for (int n = 0; n < N; n++) {
    const uint32_t r = pack_bf16(x[n][0], x[n][1]);
    q[n] = bfma2(r, 0x3e353e35u, bmul2(r, 0x379e379eu));
    x[n][0] = bf_lo(q[n]);
    x[n][1] = bf_hi(q[n]);
  }
#pragma unroll
  for (int n = 0; n < N / 2; n++)
    mx[n] = bmax2(__byte_perm(q[2 * n], q[2 * n + 1], 0x5410), __byte_perm(q[2 * n], q[2 * n + 1], 0x7632));
#pragma unroll
  for (int o = 1; o <= 2; o++)
#pragma unroll
    for (int n = 0; n < N / 2; n++) mx[n] = bmax2(mx[n], __shfl_xor_sync(0xffffffffu, mx[n], o));
  float m[N], t[N];
#pragma unroll
  for (int n = 0; n < N / 2; n++) {
    m[2 * n] = bf_lo(mx[n]);
    m[2 * n + 1] = bf_hi(mx[n]);
  }
#pragma unroll
  for (int n = 0; n < N; n++) {
    const float nm = -m[n] * c2;
    x[n][0] = ex2(fmaf(x[n][0], c2, nm));
    x[n][1] = ex2(fmaf(x[n][1], c2, nm));
    t[n] = x[n][0] + x[n][1];
  }
#pragma unroll
  for (int o = 1; o <= 2; o++)
#pragma unroll
    for (int n = 0; n < N; n++) t[n] += __shfl_xor_sync(0xffffffffu, t[n], o);
#pragma unroll
  for (int n = 0; n < N; n++) {
    const float inv = rcp(t[n]);
    pp[n] = pack_bf16(x[n][0] * inv, x[n][1] * inv);
  }
}
__device__ __forceinline__ void attn_pv(uint32_t dst, const uint32_t (&va)[4], const uint32_t (&vb)[4], uint32_t pp,
                                        uint32_t maskLE) {
  const uint32_t b0 = pp & ~maskLE, b1 = pp & maskLE;
  float oa[4], ob[4];
  mma16816_z(oa, va[0], va[1], va[2], va[3], b0, b1);
  mma16816_z(ob, vb[0], vb[1], vb[2], vb[3], b0, b1);
  stsm4t(dst, pack_bf16(oa[0], oa[1]), pack_bf16(oa[2], oa[3]), pack_bf16(ob[0], ob[1]), pack_bf16(ob[2], ob[3]));
}

template <int MODE>
__global__ void __cluster_dims__(2, 1, 1) __launch_bounds__(NTHREADS, 1)
fused_kernel(const Params p, const __grid_constant__ CUtensorMap tmX, const __grid_constant__ CUtensorMap tmW,
             const __grid_constant__ CUtensorMap tmWo,
             const __grid_constant__ CUtensorMap tmQ,
             const __grid_constant__ CUtensorMap tmXh, const __grid_constant__ CUtensorMap tmWh) {
  extern __shared__ __align__(1024) uint8_t smem[];
  const uint32_t sb = smem_u32(smem);
  const uint32_t bars = sb + OFF_BAR;
  const int tid = threadIdx.x, lane = tid & 31, warp = __shfl_sync(0xffffffffu, tid >> 5, 0);
  const int rank = blockIdx.x & 1;
  const bool halo_cta = blockIdx.x < 4;
  if (halo_cta && MODE != 0) return;
  int grp, mem;
  {
    const int t = (blockIdx.x >> 1) - 4, u = t - 32;
    const int q7 = (u * 37) >> 8;
    const bool lo = (unsigned)t < 32u, mid = (unsigned)u < 28u;
    grp = lo ? (t & 7) : (mid ? 1 + u - 7 * q7 : 0);
    mem = lo ? (t >> 3) : (mid ? 4 + q7 : (t < 0 ? t + 6 : t - 54));
  }
  const int rg = (grp >> 2) * 4 + (mem >> 1), hp = (grp & 3) * 4 + (mem & 1) * 2 + rank;
  const int rb2 = (grp >> 2) * 8 + mem, cb2 = (grp & 3) * 2 + rank;
  const int chb = grp * 16 + mem * 2 + rank;
  const int cta = rg * 16 + hp;
  const int par = rg >> 2, gidx = rg & 3;

  if (tid < 256 && !halo_cta && MODE != 2) {
    const int r = tid >> 3, c = tid & 7;
    const uint32_t so = r * 128 + ((c ^ (r & 7)) << 4);
    const __nv_bfloat16* wg0 = p.w + (size_t)r * (3 * DM) + hp * 64 + c * 8;
    const __nv_bfloat16* xg0 = p.x + (size_t)(2 * (gidx * 256 + r) + par) * DM + c * 8;
#pragma unroll
    for (int j = 0; j < 3; j++) cp_async16n(sb + OFF_1B + j * 4096 + so, wg0 + j * DM);
#pragma unroll
    for (int i = 0; i < 8; i++) cp_async16n(sb + i * 4096 + so, xg0 + (size_t)i * 64 * DM);
    asm volatile("cp.async.commit_group;\n" ::: "memory");
  }
  if (tid == 256) {
    prefetch_tmap(halo_cta ? &tmXh : &tmX);
#pragma unroll
    for (int i = 0; i < NS1B; i++) mbar_init(bars + 8 * (BAR_FULLB + i), 1);
#pragma unroll
    for (int i = 0; i < NS1A; i++) mbar_init(bars + 8 * (BAR_FULLA + i), 1);
    asm volatile("fence.mbarrier_init.release.cluster;\n" ::: "memory");
    if (!halo_cta && MODE != 2) {
      mbar_expect_tx(bars + 8 * (BAR_FULLB + 1), STG1B);
      tma_load_3d(sb + OFF_1B + 1 * STG1B, &tmW, bars + 8 * (BAR_FULLB + 1), hp * 64, 32, 0);
      mbar_expect_tx(bars + 8 * (BAR_FULLB + 2), STG1B);
      tma_load_3d(sb + OFF_1B + 2 * STG1B, &tmW, bars + 8 * (BAR_FULLB + 2), hp * 64, 64, 0);
    } else {
      prefetch_tmap(&tmWh);
    }
  } else if (tid == 288) {
#pragma unroll
    for (int i = 0; i < NS1A; i++) mbar_init(bars + 8 * (BAR_EMPTYA + i), 4);
#pragma unroll
    for (int i = 0; i < NS1B; i++) mbar_init(bars + 8 * (BAR_EMPTYB + i), 2);
    asm volatile("fence.mbarrier_init.release.cluster;\n" ::: "memory");
  } else if (tid == 320) {
#pragma unroll
    for (int i = 0; i < NS2; i++) {
      mbar_init(bars + 8 * (BAR_FULL2 + i), 1);
      mbar_init(bars + 8 * (BAR_EMPTY2 + i), 4);
    }
    mbar_init(bars + 8 * BAR_DEAD, 2);
    mbar_init(bars + 8 * (BAR_DEAD + 1), 2);
    mbar_init(bars + 8 * BAR_X, 2);
    mbar_init(bars + 8 * BAR_REL, 2);
    asm volatile("fence.mbarrier_init.release.cluster;\n" ::: "memory");
  } else if (tid == 352) {
    mbar_init(bars + 8 * BAR_T, 1);
    mbar_init(bars + 8 * BAR_UH, 3);
    mbar_init(bars + 8 * BAR_LFREE, 4);
    mbar_init(bars + 8 * BAR_LAND, 1);
    mbar_init(bars + 8 * BAR_U, 1);
    mbar_init(bars + 8 * BAR_Q, 1);
    mbar_init(bars + 8 * BAR_STG, 9);
    asm volatile("fence.mbarrier_init.release.cluster;\n" ::: "memory");
  }
  if (warp == 8) PROF2(23);
  cluster_sync_all();
  if (warp == 8) PROF2(24);

  if (warp >= 8) {
    const int hw = warp - 8;
    const int lr = lane & 7, lm = lane >> 3;
    auto g1_issue_a = [&](int j, int s) {
      const uint32_t fb = bars + 8 * (BAR_FULLA + s);
      mbar_expect_tx(fb, STG1A);
      tma_load_3d_mc(sb + s * STG1A + rank * 16384, &tmX, fb, j * 64, par, gidx * 256 + rank * 128);
    };
    auto g1_issue_b = [&](int kb, int s) {
      const uint32_t fb = bars + 8 * (BAR_FULLB + s);
      mbar_expect_tx(fb, STG1B);
      tma_load_3d(sb + OFF_1B + s * STG1B, &tmW, fb, hp * 64, kb * 32, 0);
    };
    asm volatile("setmaxnreg.dec.sync.aligned.u32 %0;\n" :: "n"(REG_HELP));

    if (halo_cta) {
      if (hw == 0) {
        int s = 0, ph = 1;
#pragma unroll 1
        for (int kb = 0; kb < 16; kb++) {
          mbar_wait(bars + 8 * (BAR_EMPTYB + s), ph);
          const uint32_t fb = bars + 8 * (BAR_FULLB + s), st = sb + s * STGH;
          if (elect_one()) {
            mbar_expect_tx(fb, STGH);
            tma_load_4d(st, &tmXh, fb, kb * 64, 248, 0, 0);
            tma_load_3d(st + 8192, &tmWh, fb, 0, kb * 64, 16 + blockIdx.x * 4);
            tma_load_3d(st + 8192 + 32768, &tmWh, fb, 0, kb * 64, 32 + blockIdx.x * 4);
          }
          if (++s == 3) { s = 0; ph ^= 1; }
        }
      }
      __syncwarp();
    } else if (hw == 0) {
      uint32_t epoch = 0;
      if (lane < (MODE == 2 ? NS2 : 2)) mbar_arrive_cluster_n(mapa(bars, rank) + 8 * (BAR_EMPTY2 + lane), 4);
      if (MODE != 2) {
      epoch = ld_relaxed(g_flag_o + 2 * cta) + 1;
      if (lane == 0) {
        mbar_expect_tx(bars + 8 * BAR_U, 32768);
        mbar_expect_tx(bars + 8 * BAR_LAND, 32768);
        mbar_expect_tx(bars + 8 * BAR_Q, 32768);
        mbar_expect_tx(bars + 8 * BAR_T, T_END);
      }
      {
        int sa = 1, pha = 1, sbb = 2, phb = 1;
#pragma unroll 1
        for (int kb = 2; kb < 32; kb++) {
          if (!(kb & 1)) {
            mbar_wait(bars + 8 * (BAR_EMPTYA + sa), pha);
            if (elect_one()) g1_issue_a(kb >> 1, sa);
            if (++sa == NS1A) { sa = 0; pha ^= 1; }
          }
          mbar_wait(bars + 8 * (BAR_EMPTYB + sbb), phb);
          if (kb > 2 && elect_one()) g1_issue_b(kb, sbb);
          __syncwarp();
          if (kb >= PF0 && kb < PF0 + 12)
            prefetch_l2((kb < PF0 + 8 ? p.q + (size_t)chb * 16384 + (kb - PF0) * 2048 : p.wo + (size_t)chb * 8192 + (kb - PF0 - 8) * 2048) + lane * 64);
          if (kb == 4) PROF2(27);
          if (kb == 1) PROF2(38);
          if (kb == 2) PROF2(39);
          if (++sbb == NS1B) { sbb = 0; phb ^= 1; }
        }
      }
      static_assert(32 % NS1B == 2 && (32 / NS1B) % 2 == 0 && OFF_Q == OFF_1B && 2 * STG1B == 6 * 4096, "slots / parity of these loads");
      const uint8_t* tab = reinterpret_cast<const uint8_t*>(g_tab);
      if (lane == 0) {
        prefetch_tmap(&tmWo);
        prefetch_tmap(&tmQ);
        bulk_load(sb + OFF_T + T_A1, tab + T_A1, T_END - T_A1, bars + 8 * BAR_T);
        mbar_wait(bars + 8 * (BAR_EMPTYB + 2), 1);
        tma_load_5d(sb + OFF_Q + 6 * 4096, &tmQ, bars + 8 * BAR_Q, (chb & ~1) * 8, rank * 32 + 24);
        tma_load_5d(sb + OFF_Q + 7 * 4096, &tmQ, bars + 8 * BAR_Q, (chb & ~1) * 8, rank * 32 + 28);
        if (gidx != 0) wait_flag(g_flag_h + (hp >> 2), epoch);
      }
      __syncwarp();
      {
        uint4 hk0 = make_uint4(0, 0, 0, 0), hk1 = hk0, hv0 = hk0, hv1 = hk0;
        if (gidx != 0) {
          const uint4* src = g_halo + cta * 128 + lane;
          hk0 = __ldcg(src); hk1 = __ldcg(src + 32); hv0 = __ldcg(src + 64); hv1 = __ldcg(src + 96);
        }
        if (lane == 0) {
          mbar_wait(bars + 8 * (BAR_EMPTYB + 3), 1);
          bulk_load(sb + OFF_T, tab, T_TW, bars + 8 * BAR_T);
        }
        __syncwarp();
        PROF2(18);
        sts128(sb + OFF_L0 + 1024 + lane * 16, hk0.x, hk0.y, hk0.z, hk0.w);
        sts128(sb + OFF_L0 + 1536 + lane * 16, hk1.x, hk1.y, hk1.z, hk1.w);
        stsm4(sb + OFF_L0 + lr * 128 + ((lm ^ lr) << 4), hv0.x, hv0.y, hv0.z, hv0.w);
        stsm4(sb + OFF_L0 + lr * 128 + (((4 + lm) ^ lr) << 4), hv1.x, hv1.y, hv1.z, hv1.w);
        __syncwarp();
        if (lane == 0) {
          mbar_arrive(bars + 8 * BAR_STG);
          mbar_wait(bars + 8 * (BAR_EMPTYB + 4), 1);
          bulk_load(sb + OFF_T + T_TW, tab + T_TW, T_A1 - T_TW, bars + 8 * BAR_T);
          mbar_wait(bars + 8 * BAR_EMPTYB, 0);
#pragma unroll 1
          for (int i = 0; i < 6; i++) tma_load_5d(sb + OFF_Q + i * 4096, &tmQ, bars + 8 * BAR_Q, (chb & ~1) * 8, rank * 32 + i * 4);
        }
        __syncwarp();
      }
      }
      if (MODE != 1) {
        auto korder = [&](int i) { return MODE == 2 ? i : g2_k(hp, i); };
        if (MODE == 0) {
          mbar_wait(bars + 8 * (BAR_EMPTY2 + 2), 0);
          if (elect_one()) {
            mbar_expect_tx(bars + 8 * BAR_FULL2, STG2);
            tma_load_3d(sb + g2_b(0), &tmWo, bars + 8 * BAR_FULL2, 0, korder(0) * 64, cb2 * 2);
            tma_load_3d(sb + g2_b(1), &tmWo, bars + 8 * (BAR_FULL2 + 1), 0, korder(1) * 64, cb2 * 2);
          }
        }
        PROF2(20);
        const __nv_bfloat16* osrc = g_o + (size_t)(rb2 >> 1) * 16 * 16384 + ((rb2 & 1) * 2 + rank) * 4096;
        const uint32_t* flag = g_flag_o + (rb2 >> 1) * 32 + korder(lane & 15) * 2 + (rb2 & 1);
        uint32_t ready = MODE == 0 ? 0u : ~0u;
        int s = MODE == 0 ? 2 : 0, ph = 0;
        uint32_t pv = epoch - 1;
#pragma unroll 1
        for (int i = s; i < 16; i++) {
          const int kb = korder(i);
          const uint32_t fb = bars + 8 * (BAR_FULL2 + s);
          if (!((ready >> i) & 1)) {
            int n = 0;
            do {
              ready |= __ballot_sync(0xffffffffu, ld_acquire(flag) == epoch);
            } while (!((ready >> i) & 1) && ++n < SPIN_LIMIT);
            fence_async_all();
          }
          if (i == 2) PROF(21);
          mbar_wait(bars + 8 * (BAR_EMPTY2 + s), ph);
          if (elect_one()) {
            mbar_expect_tx(fb, STG2);
            asm volatile(
                "cp.async.bulk.shared::cluster.global.mbarrier::complete_tx::bytes.multicast::cluster [%0], [%1], %2, [%3], %4;\n"
                ::"r"(sb + g2_a(s) + rank * 8192), "l"(osrc + kb * 16384), "r"(8192), "r"(fb), "h"((uint16_t)3) : "memory");
            if (MODE != 0 || i >= 4) tma_load_3d(sb + g2_b(s), &tmWo, fb, 0, kb * 64, cb2 * 2);
          }
          if (++s == NS2) { s = 0; ph ^= 1; }
          if (i == LOOKAHEAD) pv = ld_relaxed(flag);
          if (i == 8) {
            ready |= __ballot_sync(0xffffffffu, pv == epoch);
            asm volatile("fence.acquire.gpu;\n" ::: "memory");
            fence_async_all();
          }
          if (i == 3) PROF(37);

        }
      }
      __syncwarp();
    } else if (MODE != 2) {
      {
        const int g = lane >> 2, t = lane & 3;
        uint32_t w[2][4];
#pragma unroll
        for (int h = 0; h < 2; h++) {
          const uint2 x = __ldg(reinterpret_cast<const uint2*>(p.shift_k + ((chb & ~1) * 8 + h * 8 + g) * 4));
          w[h][0] = __byte_perm(x.x, x.x, 0x1010);
          w[h][1] = __byte_perm(x.x, x.x, 0x3232);
          w[h][2] = __byte_perm(x.y, x.y, 0x1010);
          w[h][3] = __byte_perm(x.y, x.y, 0x3232);
        }
        auto swz = [](int r) { return (((r & 29) | ((r ^ (r >> 2)) & 2)) << 5) | (r & 16); };
        const uint32_t kring = sb + OFF_H + (hw - 1) * 8192, vring = kring + 4096;
        const int s0 = rank * 32 + (hw - 1) * 11, s1 = hw == 3 ? rank * 32 + 32 : s0 + 11;
        const size_t goff = (size_t)(lane >> 1) * DM + (chb & ~1) * 8 + (lane & 1) * 8;
        const __nv_bfloat16* kg = p.k + goff;
        const __nv_bfloat16* vg = p.v + goff;
        const uint32_t d0 = swz(lane >> 1) ^ ((lane & 1) << 4), d1 = swz(16 + (lane >> 1)) ^ ((lane & 1) << 4);
        auto issue = [&](int st) {
          const uint32_t so = (st & 3) << 10;
          cp_async16(kring + so + d0, kg + (size_t)st * 32 * DM, 16);
          cp_async16(kring + so + d1, kg + (size_t)(st * 32 + 16) * DM, 16);
          cp_async16(vring + so + d0, vg + (size_t)st * 32 * DM, 16);
          cp_async16(vring + so + d1, vg + (size_t)(st * 32 + 16) * DM, 16);
        };
        const int xa = 8 * (lr >> 1) + 2 * lm + (lr & 1), xb = 8 * (lr >> 1) - 4 + 2 * (lm & 1) + (lr & 1);
        const uint32_t la = swz(xa), lb = swz(xb & 31);
        const int backb = xb < 0 ? 1 : 0;
        const uint32_t ud[2] = {mapa(sb + OFF_U + g * 4096 + t * 16, 0), mapa(sb + OFF_U + g * 4096 + t * 16, 1)};
        const uint32_t ub[2] = {mapa(bars + 8 * BAR_U, 0), mapa(bars + 8 * BAR_U, 1)};
        if (lane == 0) mbar_wait(bars + 8 * (BAR_FULLB + NS1B - 1), 0);
        __syncwarp();
        if (lane >= 24) cp_async16(kring + (((s0 - 1) & 3) << 10) + d1, s0 > 0 ? kg + (size_t)(s0 * 32 - 16) * DM : kg, s0 > 0 ? 16 : 0);
        issue(s0);
        asm volatile("cp.async.commit_group;\n" ::: "memory");
        issue(s0 + 1);
        asm volatile("cp.async.commit_group;\n" ::: "memory");
#pragma unroll 1
        for (int st = s0; st < s1; st++) {
          if (st + 2 < s1) issue(st + 2);
          if (hw == 1 && st - s0 < 8) prefetch_l2(p.ssm_k + (size_t)(chb * 8 + st - s0) * SEQ + lane * 64);
          if (hw == 2 && st == s0 + 4 && lane < 2) prefetch_l2(g_tab + (chb * 2 + lane) * 32);
          const uint32_t uo = (st ^ ((g ^ (st >> 2)) & 1)) * 64;
          asm volatile("cp.async.commit_group;\n" ::: "memory");
          asm volatile("cp.async.wait_group 2;\n" ::: "memory");
          __syncwarp();
#pragma unroll
          for (int h = 0; h < 2; h++) {
            uint32_t e[6], vv[4], e4[4];
            ldsm4t(e4, kring + ((st & 3) << 10) + (la ^ (h << 4)));
            ldsm2t(e[0], e[1], kring + (((st - backb) & 3) << 10) + (lb ^ (h << 4)));
            ldsm4t(vv, vring + ((st & 3) << 10) + (la ^ (h << 4)));
            e[2] = e4[0]; e[3] = e4[1]; e[4] = e4[2]; e[5] = e4[3];
            uint32_t o[5];
#pragma unroll
            for (int i = 0; i < 5; i++) o[i] = __byte_perm(e[i], e[i + 1], 0x5432);
#pragma unroll
            for (int i = 0; i < 4; i++) {
              uint32_t a = bmul2(o[i], w[h][3]);
              a = bfma2(e[i + 1], w[h][2], a);
              a = bfma2(o[i + 1], w[h][1], a);
              a = bfma2(e[i + 2], w[h][0], a);
              vv[i] = bmul2(a, vv[i]);
            }
            st_async128(ud[h] + uo, ub[h], vv[0], vv[1], vv[2], vv[3]);
          }
          __syncwarp();
        }
        PROF(16);
      }
      {
        const int rw = (lane >> 3) + (lane & 4), ck = lane & 3;
        const uint32_t so = rw * 64 + ck * 16, dof = rw * 128 + ((ck ^ rw) << 4);
        const uint8_t* hsrc = reinterpret_cast<const uint8_t*>(p.ssm_k + (size_t)chb * 8 * SEQ) + so;
        const float dv = lane < 8 ? __bfloat162float(p.ssm_D[chb * 8 + lane]) : 0.f;
        uint32_t x[32];
        auto load = [&](const uint8_t* src, int i) {
          asm volatile("ld.v4.u32 {%0,%1,%2,%3}, [%4];\n" : "=r"(x[4 * i]), "=r"(x[4 * i + 1]), "=r"(x[4 * i + 2]), "=r"(x[4 * i + 3])
                       : "l"(src + i * 512) : "memory");
        };
#pragma unroll
        for (int i = 0; i < 8; i++) load(hsrc + (hw - 1) * 4096, i);
        nb_sync(NB_HELP3, 96);
        mbar_wait(bars + 8 * BAR_U, 0);
        int eh = 0;
#pragma unroll 1
        for (int n = 2 * (hw - 1); n < 16; n += (n & 1) ? 5 : 1) {
          const int c = n >> 1;
          const uint8_t* nsrc = (n & 1) ? hsrc + (c < 5 ? c + 3 : c) * 4096
                                        : smem + OFF_U + c * 4096 + (so ^ (((c ^ (lane >> 2)) & 1) << 6));
          const uint32_t dst = sb + ((n & 1) ? OFF_U : OFF_H) + c * 4096 + dof;
          const float dc = __shfl_sync(0xffffffffu, dv, c);
          const float h0 = bf_lo(x[0]) + ((lane | (n & 1)) == 0 ? dc : 0.f), h1 = bf_hi(x[0]);
          x[0] = pack_bf16(h0, h1);
          uint32_t m[2] = {x[0], x[1]};
#pragma unroll
          for (int i = 2; i < 32; i++) asm("max.xorsign.abs.bf16x2 %0, %0, %1;\n" : "+r"(m[i & 1]) : "r"(x[i]));
          asm("max.xorsign.abs.bf16x2 %0, %0, %1;\n" : "+r"(m[0]) : "r"(m[1]));
          const uint32_t e = max(__reduce_max_sync(0xffffffffu, max((m[0] >> 7) & 255u, (m[0] >> 23) & 255u)), 5u);
          const uint32_t sc = (259u - e) * 0x00800080u;
#pragma unroll
          for (int i = 0; i < 8; i++) {
            uint32_t o[4];
#pragma unroll
            for (int j = 0; j < 4; j++) {
              const uint32_t v = bmul2(x[4 * i + j], sc);
              asm("cvt.rn.f16x2.f32 %0, %1, %2;\n" : "=r"(o[j]) : "f"(bf_hi(v)), "f"(i + j == 0 ? h0 * bf_hi(sc) : bf_lo(v)));
            }
            sts128((dst + (i & 3) * 1024) ^ ((i >> 2) << 6), o[0], o[1], o[2], o[3]);
            load(nsrc, i);
          }
          if (n & 1) {
            const int f = min(max((int)e + eh - 129, 0), 254);
            if (lane == 0) asm volatile("st.shared.u32 [%0], %1;\n" ::"r"(sb + OFF_SC + c * 4), "r"(f << 23) : "memory");
          }
          eh = e;
        }
        fence_async_smem();
        __syncwarp();
        if (lane == 0) mbar_arrive(bars + 8 * BAR_UH);
        PROF(32);
      }
      if (hw < 3) {
        const uint32_t rb = mapa(bars, lane & 1);
        const uint32_t epoch = ld_relaxed(g_flag_o + 2 * cta + hw - 1) + 1;
        const bool own = hw - 1 == (rb2 & 1);
        nb_sync(NB_OREADY + hw - 1, 160);
        if (lane < 2) {
          mbar_arrive_cluster(rb + 8 * (BAR_EMPTY2 + 2));
          mbar_arrive_cluster(rb + 8 * (BAR_EMPTY2 + 3));
        }
        if (lane == 0) {
          if (own) mbar_arrive(bars + 8 * BAR_X);
          if (rank) mbar_wait(bars + 8 * BAR_REL, 0);
          asm volatile("cp.async.bulk.global.shared::cta.bulk_group [%0], [%1], %2;\n" ::"l"(g_o + (size_t)cta * 16384 + (hw - 1) * 8192),
                       "r"(sb + OFF_OP + (own ? 16384 : 0)), "r"(16384) : "memory");
          bulk_commit();
          bulk_wait0();
          if (own) mbar_expect_tx(bars + 8 * (BAR_FULL2 + 1), 16384);
          else mbar_arrive_cluster(mapa(bars, rank ^ 1) + 8 * BAR_X);
          st_release(g_flag_o + 2 * cta + hw - 1, epoch);
        }
        __syncwarp();
        if (rank == 0 && lane < 2) mbar_arrive_cluster(rb + 8 * BAR_REL);
        __syncwarp();
        PROF(rank ? 17 : 19);
      } else {
        mbar_wait(bars + 8 * BAR_REL, 0);
        if (MODE == 0) {
          mbar_wait(bars + 8 * BAR_X, 0);
          if (elect_one())
            asm volatile("cp.async.bulk.shared::cluster.shared::cta.mbarrier::complete_tx::bytes [%0], [%1], %2, [%3];\n"
                         ::"r"(mapa(sb + OFF_OP, rank ^ 1)), "r"(sb + OFF_OP + 16384), "r"(16384),
                         "r"(mapa(bars + 8 * BAR_FULL2, rank ^ 1)) : "memory");
        }
        if (MODE == 0) {
          mbar_wait(bars + 8 * BAR_DEAD, 0);
          if (elect_one()) {
            tma_load_3d(sb + g2_b(2), &tmWo, bars + 8 * (BAR_FULL2 + 2), 0, g2_k(hp, 2) * 64, cb2 * 2);
            tma_load_3d(sb + g2_b(3), &tmWo, bars + 8 * (BAR_FULL2 + 3), 0, g2_k(hp, 3) * 64, cb2 * 2);
          }
        }
        __syncwarp();
      }
      {
        const int c8 = (4 * (lr >> 1) + 2 * (lm & 1) + (lr & 1)) & 7;
        const bool own = (lr >> 2) == rank;
        const uint32_t ya = sb + (own ? y_slot(c8 & 1, c8 >> 1) : OFF_LAND + c8 * 2048);
        const uint32_t yx = ((lm >> 1) ^ lr) << 4;
        const int row = (lane >> 3) * 8 + ((lane >> 2) & 1);
        uint2* og = reinterpret_cast<uint2*>(p.out + (size_t)(rank * 1024 + row) * (2 * DM) + (chb & ~1) * 8 + (lane & 3) * 4);
        const uint32_t qa = sb + OFF_Q + lane * 8;
        mbar_wait(bars + 8 * BAR_Q, 0);
        mbar_wait(bars + 8 * BAR_LAND, 0);
        PROF(33);
        const uint32_t t0 = clock();
#pragma unroll 1
        for (int j = hw - 1; j < 16; j += 3) {
          uint32_t y[4][4];
          uint2 q[8];
          while ((uint32_t)clock() - t0 < j * PACE) __nanosleep(40);
          const uint32_t qj = qa + j * 2048;
#pragma unroll
          for (int i = 0; i < 4; i++) ldsm4t(y[i], ya + j * 128 + (yx ^ (i << 5)));
#pragma unroll
          for (int i = 0; i < 8; i++) q[i] = lds64(qj + i * 256);
#pragma unroll
          for (int i = 0; i < 8; i++)
            og[(size_t)(j * 64 + (i >> 2) * 32 + (i & 3) * 2) * (2 * DM / 4)] =
                make_uint2(bmul2(q[i].x, y[i >> 1][2 * (i & 1)]), bmul2(q[i].y, y[i >> 1][2 * (i & 1) + 1]));
        }
      }
      PROF(22);
    }
    cluster_sync_all();
  } else {
    asm volatile("setmaxnreg.inc.sync.aligned.u32 %0;\n" :: "n"(REG_MATH));
    if (warp == 0) PROF2(26);
    const int wg = warp >> 2;
    const int wtid = tid & 127;
    const bool signaller = (wtid == 0) || (wtid == 32);
    const uint32_t rbars = mapa(bars, wtid >> 5 & 1);

    if (halo_cta) {
      const uint32_t epoch = ld_relaxed(g_flag_h + blockIdx.x) + 1;
      float acc0[64], acc1[64];
      int s = 0, ph = 0;
#pragma unroll 1
      for (int kb = 0; kb < 16; kb++) {
        mbar_wait(bars + 8 * (BAR_FULLB + s), ph);
        const uint32_t st = sb + s * STGH;
        const uint64_t da = mkdesc(st, 16, 1024, 1);
        const uint64_t db = mkdesc(st + 8192 + wg * 32768, 8192, 1024, 1);
        wg_fence();
#pragma unroll
        for (int kk = 0; kk < 4; kk++) {
          wgmma_n128(acc0, da + 2 * kk, db + 128 * kk, kb + kk);
          wgmma_n128(acc1, da + 2 * kk, db + 1024 + 128 * kk, kb + kk);
        }
        wg_commit();
        wg_wait<0>();
        if (wtid == 0) mbar_arrive(bars + 8 * (BAR_EMPTYB + s));
        if (++s == 3) { s = 0; ph ^= 1; }
      }
      fence_regs(acc0);
      fence_regs(acc1);
      if ((warp & 3) != 3) {
#pragma unroll
        for (int hh = 0; hh < 2; hh++) {
          uint4* dst = g_halo + ((hh * 4 + (warp & 3) + 1) * 16 + blockIdx.x * 4) * 128 + wg * 64 + lane;
#pragma unroll
          for (int j = 0; j < 4; j++) {
            const int o = 16 * j + 2 * hh;
            dst[(j >> 1) * 128 + (j & 1) * 32] =
                make_uint4(pack_bf16(acc0[o], acc0[o + 1]), pack_bf16(acc0[o + 4], acc0[o + 5]),
                           pack_bf16(acc0[o + 8], acc0[o + 9]), pack_bf16(acc0[o + 12], acc0[o + 13]));
            dst[(2 + (j >> 1)) * 128 + (j & 1) * 32] =
                make_uint4(pack_bf16(acc1[o], acc1[o + 1]), pack_bf16(acc1[o + 4], acc1[o + 5]),
                           pack_bf16(acc1[o + 8], acc1[o + 9]), pack_bf16(acc1[o + 12], acc1[o + 13]));
          }
        }
      }
      nb_sync(NB_G1DONE, 256);
      if (tid == 0) st_release(g_flag_h + blockIdx.x, epoch);
      PROF(36);
      cluster_sync_all();
      return;
    }

    if (MODE != 2) {
    {
      float acc0[96], acc1[96];
      int sa = 0, pha = 0, sbb = 0, phb = 0;
      asm volatile("cp.async.wait_group 0;\n" ::: "memory");
      fence_async_smem();
      nb_sync(NB_FIRST, 256);
      if (tid == 0) {
        mbar_arrive(bars + 8 * BAR_FULLA);
        mbar_arrive(bars + 8 * BAR_FULLB);
      }
      PROF(0 + wg);
#pragma unroll 1
      for (int kb = 0; kb < 30; kb++) {
        if (!(kb & 1)) mbar_wait(bars + 8 * (BAR_FULLA + sa), pha);
        mbar_wait(bars + 8 * (BAR_FULLB + sbb), phb);
        if (kb == 0) PROF2(0 + wg);
        if (kb == 4 && wg == 0) PROF2(28);
        if (kb == 8 && wg == 0) PROF2(29);
        if (kb == 16 && wg == 0) PROF2(30);
        const uint64_t da = mkdesc(sb + sa * STG1A + wg * 16384 + (kb & 1) * 64, 16, 1024, 1);
        const uint64_t db = mkdesc(sb + OFF_1B + sbb * STG1B, 4096, 1024, 1);
        wg_fence();
        wgmma_n192(acc0, da, db, kb);
        wgmma_n192(acc1, da + 512, db, kb);
        wgmma_n192(acc0, da + 2, db + 128, 1);
        wgmma_n192(acc1, da + 514, db + 128, 1);
        wg_commit();
        wg_wait<1>();
        if (kb > 0) {
          if (wtid == 64) mbar_arrive(bars + 8 * (BAR_EMPTYB + (sbb == 0 ? NS1B - 1 : sbb - 1)));
          if (!(kb & 1) && signaller) mbar_arrive_cluster(rbars + 8 * (BAR_EMPTYA + (sa == 0 ? NS1A - 1 : sa - 1)));
        }
        if (++sbb == NS1B) { sbb = 0; phb ^= 1; }
        if ((kb & 1) && ++sa == NS1A) { sa = 0; pha ^= 1; }
      }
      const int blk0 = wg * 8 + (warp & 3);
      const int lr = lane & 7, lm = lane >> 3;
      const bool le0 = 2 * (lane & 3) <= (lane >> 2), le1 = 2 * (lane & 3) + 1 <= (lane >> 2);
      const uint32_t maskLE = (le0 ? 0x0000FFFFu : 0u) | (le1 ? 0xFFFF0000u : 0u);
      uint32_t k0[2][2][4], k1[2][2][4], qa[2][2][8];
      float l[2][2][4];
      {
        static_assert(15 % NS1A == 0 && 30 % NS1B == 0, "slots of the last k blocks");
        mbar_wait(bars + 8 * BAR_FULLA, 1);
        mbar_wait(bars + 8 * BAR_FULLB, 0);
        mbar_wait(bars + 8 * (BAR_FULLB + 1), 0);
        const uint64_t da = mkdesc(sb + wg * 16384, 16, 1024, 1);
        const uint64_t db = mkdesc(sb + OFF_1B, 4096, 1024, 1);
        wg_fence();
#pragma unroll
        for (int i = 0; i < 4; i++) wgmma_n192(acc0, da + 2 * i, db + (i >> 1) * (STG1B >> 4) + (i & 1) * 128, 1);
        wg_commit();
        wg_wait<1>();
        if (wtid == 64) mbar_arrive(bars + 8 * (BAR_EMPTYB + NS1B - 1));
#pragma unroll
        for (int i = 0; i < 2; i++) wgmma_n192(acc1, da + 512 + 2 * i, db + (i >> 1) * (STG1B >> 4) + (i & 1) * 128, 1);
        wg_commit();
        wg_wait<1>();
        fence_regs(acc0);
        attn_stage(sb, blk0, lane, acc0, k1[0]);
#pragma unroll
        for (int i = 2; i < 4; i++) wgmma_n192(acc1, da + 512 + 2 * i, db + (i >> 1) * (STG1B >> 4) + (i & 1) * 128, 1);
        wg_commit();
        attn_pack(acc0, qa[0], k0[0]);
        wg_wait<0>();
        fence_regs(acc1);
      }
      if (wtid == 64) mbar_arrive(bars + 8 * BAR_EMPTYB);
      PROF(2 + wg);
      attn_stage(sb, blk0 + 4, lane, acc1, k1[1]);
      __syncwarp();
      if (lane == 0) mbar_arrive(bars + 8 * BAR_STG);
      mbar_wait(bars + 8 * BAR_U, 0);
      attn_pack(acc1, qa[1], k0[1]);
      attn_own(k0[0], k1[0], le0, le1, qa[0], l[0]);
      attn_own(k0[1], k1[1], le0, le1, qa[1], l[1]);
      const uint32_t cho[2] = {(uint32_t)(((lm & 1) ^ lr) << 4), (uint32_t)(((2 + (lm & 1)) ^ lr) << 4)};
      const uint32_t obase = sb + OFF_OP + (wg == (rb2 & 1) ? 16384 : 0) + ((warp & 3) * 16 + lr) * 128;
      mbar_wait(bars + 8 * BAR_STG, 0);
      {
        uint32_t km[4][4], va[8][4], vb[8][4], pp[8];
        float x[8][2];
#pragma unroll
        for (int n = 0; n < 4; n++) {
          const int blk = blk0 + 4 * (n >> 1);
          to_arr(km[n], lds128(sb + (blk == 0 ? OFF_L0 + 1024 : OFF_KH + (blk - 1) * 2048) + (n & 1) * 512 + lane * 16));
        }
#pragma unroll
        for (int n = 0; n < 8; n++) {
          const int vr = (blk0 + 4 * ((n >> 1) & 1)) * 16 - 8 + 8 * (n >> 2) + 8 * (lm >> 1);
          const uint32_t vrow = sb + (vr < 0 ? OFF_L0 : OFF_VP + vr * 128) + lr * 128;
          ldsm4t(va[n], vrow + (cho[0] ^ ((n & 1) << 6)));
          ldsm4t(vb[n], vrow + (cho[1] ^ ((n & 1) << 6)));
        }
        const bool first = blk0 == 0 && gidx == 0;
#pragma unroll
        for (int n = 0; n < 4; n++) {
          const uint32_t(&q)[8] = qa[n >> 1][n & 1];
          float sm[4];
          mma16816_z(sm, q[0], q[1], q[2], q[3], km[n][0], km[n][1]);
          mma16816(sm, q[4], q[5], q[6], q[7], km[n][2], km[n][3]);
          if (n < 2 && first) sm[0] = sm[1] = -1e9f / 0.17677669529663687f;
          x[n][0] = le0 ? l[n >> 1][n & 1][0] : sm[0];
          x[n][1] = le1 ? l[n >> 1][n & 1][1] : sm[1];
          x[4 + n][0] = l[n >> 1][n & 1][2];
          x[4 + n][1] = l[n >> 1][n & 1][3];
        }
        quad_softmax<8>(x, pp);
#pragma unroll
        for (int n = 7; n >= 0; n--)
          attn_pv(obase + ((n >> 1) & 1) * 8192 + (n >> 2) * 1024 + (((4 * (n & 1) + lm) ^ lr) << 4), va[n], vb[n], pp[n],
                  maskLE);
      }
      fence_async_smem();
      nb_arrive(NB_OREADY + wg, 160);
    }

    {
      const int w = warp & 3;
      uint32_t a1[2][4], a4[8][4], tw[16], d1[32];
      float d4[16];
      const uint32_t tb = sb + OFF_T + wtid * 16;
      PROF(34 + wg);
      mbar_wait(bars + 8 * BAR_T, 0);
      mbar_wait(bars + 8 * BAR_UH, 0);
      to_arr(a1[0], lds128(tb + T_A1));
      to_arr(a1[1], lds128(tb + T_A1 + 2048));
      const uint64_t dx = mkdesc(sb + OFF_U + wg * 4096, OFF_H - OFF_U, 1024, 1);
      const uint64_t dz = mkdesc(sb + OFF_U + wg * 4096, 512, 128, 0);
      const uint64_t db2 = mkdesc(sb + OFF_T + T_B2, 128, 256, 0);
      wg_fence();
      hmma_n128t<0>(d1, a1[0], dx);
      hmma_n128t<1>(d1, a1[1], dx + 128);
      wg_commit();
      auto ldtw = [&](int i) {
        const uint4 v = lds128(tb + T_TW + i * 2048);
        tw[4 * i] = v.x; tw[4 * i + 1] = v.y; tw[4 * i + 2] = v.z; tw[4 * i + 3] = v.w;
      };
      ldtw(0);
      ldtw(1);
      const uint32_t za = sb + (w < 2 ? OFF_U : OFF_H) + wg * 4096 + (w & 1) * 2048 + lane * 16;
      const uint32_t yl = (wtid ^ (4 * rank + wg)) * 16;
      const uint32_t yown = mapa(sb, rank) + yl, yrem = mapa(sb + OFF_LAND + wg * 2048, rank ^ 1) + yl;
      const uint32_t yb[2] = {mapa(bars + 8 * BAR_LAND, 0), mapa(bars + 8 * BAR_LAND, 1)};
      wg_wait<0>();
      fence_regs(d1);
      nb_sync(NB_WG + wg, 128);
      auto s4 = [&](int it) {
        wg_fence();
#pragma unroll
        for (int ks = 0; ks < 8; ks++) {
          const uint64_t d = dz + (it & 1) * 512 + (ks & 3) * 64 + (ks >> 2) * ((OFF_H - OFF_U) >> 4);
          if (ks == 0) fmma_n32t<0>(d4, a4[ks], d);
          else fmma_n32t<1>(d4, a4[ks], d);
        }
        wg_commit();
      };
      auto e4 = [&](int it) {
        fence_regs(d4);
        const float sc = __uint_as_float(lds32(sb + OFF_SC + wg * 4 + it * 8));
        uint32_t r[8];
#pragma unroll
        for (int i = 0; i < 8; i++) r[i] = pack_bf16(d4[2 * i] * sc, d4[2 * i + 1] * sc);
        const uint32_t o = (yown + y_slot(wg, it)) ^ ((it >> 1) << 5), m = (yrem + it * 4096) ^ ((it >> 1) << 5);
        if (it == 0) mbar_wait(bars + 8 * BAR_LFREE, 0);
        if (it == 3) mbar_wait(bars + 8 * (BAR_DEAD + 1), 0);
        st_async128(rank ? m : o, yb[0], r[0], r[2], r[1], r[3]);
        st_async128(rank ? o : m, yb[1], r[4], r[6], r[5], r[7]);
      };
      uint32_t a2[2][2][2][4], a3[2][2][4], d2[2][2][8], d3[2][8];
      auto s2a = [&]() {
        wg_fence();
#pragma unroll
        for (int c = 0; c < 4; c++) hmma_n32<0, 0>(d2[c & 1][c >> 1], a2[0][c & 1][c >> 1], db2 + (c >> 1) * 128);
      };
      auto s2b = [&]() {
        wg_fence();
#pragma unroll
        for (int c = 0; c < 4; c++) {
          hmma_n32<1, 0>(d2[c & 1][c >> 1], a2[1][c & 1][c >> 1], db2 + (c >> 1) * 128 + 64);
          if (c & 1) wg_commit();
        }
      };
      auto s1 = [&](int it) {
        hmma_n128t<0>(d1, a1[0], dx + it * 512);
        hmma_n128t<1>(d1, a1[1], dx + it * 512 + 128);
        wg_commit();
      };
      auto done = [&](int it) {
        if (it == 0) {
          if (signaller) mbar_arrive_cluster(rbars + 8 * BAR_LFREE);
        } else if (it >= 2 && wtid == 64) {
          mbar_arrive(bars + 8 * (BAR_DEAD + it - 2));
        }
        if (w == 0) PROF3(40 + 4 * wg + it);
      };
      fft_e1<0>(d1, tw, a2[0]);
      s2a();
      fft_e1<1>(d1, tw, a2[1]);
      s2b();
      s1(1);
      ldtw(2);
      ldtw(3);
#pragma unroll
      for (int i = 0; i < 8; i++) to_arr(a4[i], lds128(tb + T_A4 + i * 2048));
#pragma unroll
      for (int it = 0; it < 4; it++) {
        if (it == 0 || it == 3) wg_wait<2>(); else wg_wait<3>();
        fence_regs(d2[0][0]);
        fence_regs(d2[1][0]);
        fft_e2<0, 0>(d2[0][0], d2[1][0], a3[0]);
        fft_e2<0, 1>(d2[0][0], d2[1][0], a3[1]);
        if (it == 0 || it == 3) wg_wait<1>(); else wg_wait<2>();
        fence_regs(d2[0][1]);
        fence_regs(d2[1][1]);
        fft_e2<1, 0>(d2[0][1], d2[1][1], a3[0]);
        fft_e2<1, 1>(d2[0][1], d2[1][1], a3[1]);
        wg_fence();
        hmma_n32<0, 0>(d3[0], a3[0][0], db2);
        hmma_n32<0, 0>(d3[1], a3[0][1], db2);
        hmma_n32<1, 0>(d3[0], a3[1][0], db2 + 64);
        hmma_n32<1, 0>(d3[1], a3[1][1], db2 + 64);
        wg_commit();
        wg_wait<1>();
        if (it > 0) e4(it - 1);
        if (it < 3) {
          fence_regs(d1);
          fft_e1<0>(d1, tw, a2[0]);
        }
        wg_wait<0>();
        fence_regs(d3[0]);
        fence_regs(d3[1]);
        if (it < 3) s2a();
        fft_e3(d3, tw, za + (it & 1) * 8192);
        if (it < 3) {
          fft_e1<1>(d1, tw, a2[1]);
          s2b();
        }
        fence_async_smem();
        nb_sync(NB_WG + wg, 128);
        done(it);
        s4(it);
        if (it < 2) s1(it + 2);
      }
      wg_wait<0>();
      if (signaller) mbar_arrive_cluster(rbars + 8 * (BAR_EMPTY2 + 4));
      e4(3);
      PROF(6 + wg);
    }
    }

    if (MODE != 1) {
      float acc[64];
      int s = 0, ph = 0;
#pragma unroll 1
      for (int kb = 0; kb < 16; kb++) {
        mbar_wait(bars + 8 * (BAR_FULL2 + s), ph);
        if (kb == 0) PROF(8 + wg);
        if (warp == 4) PROF2(40 + kb);
        const uint64_t da = mkdesc(sb + g2_a(s) + wg * 8192, 16, 1024, 1);
        const uint64_t db = mkdesc(sb + g2_b(s), 8192, 1024, 1);
        wg_fence();
        wgmma_n128(acc, da, db, kb);
        wgmma_n128(acc, da + 2, db + 128, 1);
        wgmma_n128(acc, da + 4, db + 256, 1);
        wgmma_n128(acc, da + 6, db + 384, 1);
        wg_commit();
        wg_wait<0>();
        if (kb < 16 - NS2 && signaller) mbar_arrive_cluster(rbars + 8 * (BAR_EMPTY2 + s));
        if (++s == NS2) { s = 0; ph ^= 1; }
      }
      wg_wait<0>();
      fence_regs(acc);
      PROF(10 + wg);
      const int lr = lane & 7, lm = lane >> 3;
      const uint32_t wbase = sb + warp * 2048;
      const uint32_t base = wbase + (lr + 8 * (lm & 1)) * 128;
#pragma unroll
      for (int j = 0; j < 16; j += 2) {
        const uint32_t a = base + (j >> 3) * 16384 + ((((j & 7) + (lm >> 1)) ^ lr) << 4);
        stsm4(a, pack_bf16(acc[4 * j], acc[4 * j + 1]), pack_bf16(acc[4 * j + 2], acc[4 * j + 3]),
              pack_bf16(acc[4 * j + 4], acc[4 * j + 5]), pack_bf16(acc[4 * j + 6], acc[4 * j + 7]));
      }
      __syncwarp();
      {
        const int rr = lane >> 4, ck = lane & 7, hf = (lane >> 3) & 1;
        uint4* og = reinterpret_cast<uint4*>(p.out + (size_t)(2 * ((rb2 & 7) * 128 + warp * 16 + rr) + (rb2 >> 3)) * (2 * DM) + DM + cb2 * 128 + hf * 64 + ck * 8);
        uint4 v[8];
#pragma unroll
        for (int i = 0; i < 8; i++) v[i] = lds128(wbase + hf * 16384 + (2 * i + rr) * 128 + ((ck ^ ((2 * i + rr) & 7)) << 4));
#pragma unroll
        for (int i = 0; i < 8; i++) og[(size_t)i * 4 * (2 * DM / 8)] = v[i];
      }
      PROF(12 + wg);
    }
    cluster_sync_all();
  }
}

typedef CUresult (*EncodeFn)(CUtensorMap*, CUtensorMapDataType, cuuint32_t, void*, const cuuint64_t*, const cuuint64_t*,
                             const cuuint32_t*, const cuuint32_t*, CUtensorMapInterleave, CUtensorMapSwizzle,
                             CUtensorMapL2promotion, CUtensorMapFloatOOBfill);

void make_map(EncodeFn enc, CUtensorMap* tm, const void* base, int rank, const cuuint64_t* dims, const cuuint64_t* strides,
              const cuuint32_t* box, CUtensorMapSwizzle swz) {
  cuuint32_t es[5] = {1, 1, 1, 1, 1};
  enc(tm, CU_TENSOR_MAP_DATA_TYPE_BFLOAT16, rank, const_cast<void*>(base), dims, strides, box, es,
      CU_TENSOR_MAP_INTERLEAVE_NONE, swz, CU_TENSOR_MAP_L2_PROMOTION_L2_256B, CU_TENSOR_MAP_FLOAT_OOB_FILL_NONE);
}

}

extern "C" void kernel_launch(void* const* d_in, const int* in_sizes, int n_in, void* d_out, int out_size) {
  static EncodeFn enc = nullptr;
  static bool coresident = true;
  if (!enc) {
    void* fn = nullptr;
    cudaDriverEntryPointQueryResult qr;
    cudaGetDriverEntryPoint("cuTensorMapEncodeTiled", &fn, cudaEnableDefault, &qr);
    enc = (EncodeFn)fn;
    cudaFuncSetAttribute(fused_kernel<0>, cudaFuncAttributeMaxDynamicSharedMemorySize, SMEM_BYTES);
    cudaFuncSetAttribute(fused_kernel<1>, cudaFuncAttributeMaxDynamicSharedMemorySize, SMEM_BYTES);
    cudaFuncSetAttribute(fused_kernel<2>, cudaFuncAttributeMaxDynamicSharedMemorySize, SMEM_BYTES);
    cudaLaunchConfig_t cfg = {};
    cfg.gridDim = dim3(NCTA);
    cfg.blockDim = dim3(NTHREADS);
    cfg.dynamicSmemBytes = SMEM_BYTES;
    cudaLaunchAttribute at;
    at.id = cudaLaunchAttributeClusterDimension;
    at.val.clusterDim.x = 2;
    at.val.clusterDim.y = 1;
    at.val.clusterDim.z = 1;
    cfg.attrs = &at;
    cfg.numAttrs = 1;
    int nclusters = 0;
    if (cudaOccupancyMaxActiveClusters(&nclusters, fused_kernel<0>, &cfg) == cudaSuccess) coresident = nclusters >= NCTA / 2;
    (void)cudaGetLastError();
  }
  CUtensorMap tmX, tmW, tmWo, tmQ, tmXh, tmWh;
  {
    cuuint64_t dims[3] = {1024, 2, 1024};
    cuuint64_t str[2] = {2048, 4096};
    cuuint32_t box[3] = {64, 1, 128};
    make_map(enc, &tmX, d_in[6], 3, dims, str, box, CU_TENSOR_MAP_SWIZZLE_128B);
  }
  {
    cuuint64_t dims[3] = {1024, 1024, 3};
    cuuint64_t str[2] = {6144, 2048};
    cuuint32_t box[3] = {64, 32, 3};
    make_map(enc, &tmW, d_in[7], 3, dims, str, box, CU_TENSOR_MAP_SWIZZLE_128B);
  }
  {
    cuuint64_t dims[3] = {64, 1024, 16};
    cuuint64_t str[2] = {2048, 128};
    cuuint32_t box[3] = {64, 64, 2};
    make_map(enc, &tmWo, d_in[8], 3, dims, str, box, CU_TENSOR_MAP_SWIZZLE_128B);
  }
  {
    cuuint64_t dims[5] = {1024, 2, 4, 4, 64};
    cuuint64_t str[4] = {2048, 8 * 2048, 2 * 2048, 32 * 2048};
    cuuint32_t box[5] = {16, 2, 4, 4, 4};
    make_map(enc, &tmQ, d_in[0], 5, dims, str, box, CU_TENSOR_MAP_SWIZZLE_NONE);
  }
  {
    cuuint64_t dims[4] = {1024, 256, 2, 4};
    cuuint64_t str[3] = {4096, 2048, 256 * 4096};
    cuuint32_t box[4] = {64, 8, 2, 4};
    make_map(enc, &tmXh, d_in[6], 4, dims, str, box, CU_TENSOR_MAP_SWIZZLE_128B);
  }
  {
    cuuint64_t dims[3] = {64, 1024, 48};
    cuuint64_t str[2] = {6144, 128};
    cuuint32_t box[3] = {64, 64, 4};
    make_map(enc, &tmWh, d_in[7], 3, dims, str, box, CU_TENSOR_MAP_SWIZZLE_128B);
  }
  Params p;
  p.q = (const __nv_bfloat16*)d_in[0];
  p.k = (const __nv_bfloat16*)d_in[1];
  p.v = (const __nv_bfloat16*)d_in[2];
  p.shift_k = (const __nv_bfloat16*)d_in[3];
  p.ssm_k = (const __nv_bfloat16*)d_in[4];
  p.ssm_D = (const __nv_bfloat16*)d_in[5];
  p.x = (const __nv_bfloat16*)d_in[6];
  p.w = (const __nv_bfloat16*)d_in[7];
  p.wo = (const __nv_bfloat16*)d_in[8];
  p.out = (__nv_bfloat16*)d_out;
  if (coresident) {
    fused_kernel<0><<<NCTA, NTHREADS, SMEM_BYTES>>>(p, tmX, tmW, tmWo, tmQ, tmXh, tmWh);
  } else {
    fused_kernel<0><<<4, NTHREADS, SMEM_BYTES>>>(p, tmX, tmW, tmWo, tmQ, tmXh, tmWh);
    fused_kernel<1><<<NCTA, NTHREADS, SMEM_BYTES>>>(p, tmX, tmW, tmWo, tmQ, tmXh, tmWh);
    fused_kernel<2><<<NCTA, NTHREADS, SMEM_BYTES>>>(p, tmX, tmW, tmWo, tmQ, tmXh, tmWh);
  }
}
```

```cpp
#include <cuda_runtime.h>
#include <cuda.h>
#include <cuda_bf16.h>
#include <stdint.h>

namespace {

constexpr int SEQ = 2048;
constexpr int DM = 1024;
constexpr int NCTA = 132;
constexpr int NTHREADS = 384;

constexpr int STG1A = 32768;
constexpr int NS1A = 3;
constexpr int STG1B = 12288;
constexpr int NS1B = 5;
constexpr int OFF_1B = NS1A * STG1A;
constexpr int STG2 = 32768;
constexpr int NS2 = 5;
constexpr int STGH = 73728;
constexpr int OFF_VP = 0;
constexpr int OFF_KH = 1 * STG2;
constexpr int OFF_OP = 2 * STG2;
constexpr int OFF_Q = 3 * STG2;
constexpr int T_A4 = 0, T_TW = 16384, T_B2 = 24576, T_A1 = 28672, T_END = 32768;
constexpr int OFF_U = 163840;
constexpr int OFF_H = OFF_U + 32768;
constexpr int OFF_T = OFF_U - T_END;
constexpr int OFF_LAND = 4 * STG2;
constexpr int OFF_BAR = OFF_H + 32768;
constexpr int OFF_SC = OFF_BAR + 512;
constexpr int OFF_L0 = OFF_BAR + 1024;
constexpr int SMEM_BYTES = OFF_L0 + 2048;
static_assert(OFF_T + T_A1 == OFF_1B + NS1B * STG1B && OFF_T + T_TW == OFF_1B + 4 * STG1B && OFF_LAND == OFF_T + T_A4, "layout");
static_assert(3 * STGH <= OFF_BAR && SMEM_BYTES <= 232448, "smem");

constexpr int BAR_FULLA = 0;
constexpr int BAR_EMPTYA = 3;
constexpr int BAR_FULLB = 6;
constexpr int BAR_EMPTYB = 11;
constexpr int BAR_FULL2 = 16;
constexpr int BAR_EMPTY2 = 21;
constexpr int BAR_T = 26;
constexpr int BAR_UH = 27;
constexpr int BAR_LFREE = 28;
constexpr int BAR_LAND = 29;
constexpr int BAR_U = 30;
constexpr int BAR_Q = 31;
constexpr int BAR_STG = 32;
constexpr int BAR_DEAD = 33;
constexpr int BAR_X = 35;
constexpr int BAR_REL = 36;

constexpr int NB_G1DONE = 1;
constexpr int NB_OREADY = 2;
constexpr int NB_WG = 4;
constexpr int NB_HELP3 = 6;
constexpr int NB_FIRST = 7;

#define PACE 480u
#define PF0 20
#define G2W1 0
#define SCHED 1
#define REG_MATH 224
#define REG_HELP 56
constexpr int SPIN_LIMIT = 1 << 20;

__device__ __align__(1024) __nv_bfloat16 g_o[SEQ * DM];
__device__ uint32_t g_flag_o[256];
__device__ uint32_t g_flag_h[4];
__device__ uint4 g_halo[128 * 128];
__device__ __align__(128) const uint32_t g_tab[T_END / 4] = {
0x3c003c00,0x3bf13bff,0,0xafd6a648,0x3c003c00,0x3b993bce,0,0xb505b303,0x3c003c00,0x3af63b50,0,0xb7e3b67c,
0x3c003c00,0x3a0f3a8a,0,0xb93ab89b,0x3bc33bfe,0x3b773bfa,0xb3c6aa48,0xb5c2acb5,0x3a6d3b3b,0x389b3a4f,0xb8c4b6d7,0xba8ab8ec,
0x381d395f,0x26483505,0xbaddb9ed,0xbbffbb99,0x30b23564,0xb848b444,0xbbeabb88,0xbac2bbb6,0x3b0e3bf6,0x3a8a3bf1,0xb78bae46,0xb89bafd6,
0x34a53913,0xa6483732,0xbba8ba2f,0xbbffbb25,0xb78bae46,0xbac2b7e3,0xbb0ebbf6,0xb848baf6,0xbba8ba2f,0xbb50bbfa,0xb4a5b913,0x367cacb5,
0x39ed3bea,0x393a3be2,0xb95fb0b2,0xba0fb179,0xb56433c6,0xb8ec2648,0xbb88bbc3,0xba4fbbff,0xbbfeba6d,0xbb25bbce,0xaa48b8c4,0x3732b303,
0xb6d7badd,0x3444b67c,0x3b3b381d,0x3bb63b50,0x38723bd9,0x37323bce,0xbaa7b23e,0xbb25b303,0xbaa7b23e,0xbbb6b67c,0xb872bbd9,0xb444bb50,
0xb872bbd9,0xacb5ba8a,0x3aa7323e,0x3bfa389b,0x3aa7323e,0x3bf139cb,0x38723bd9,0xafd63984,0x35643bc3,0x33033bb6,0xbb88b3c6,0xbbceb444,
0xbbfeb8c4,0xbb77ba0f,0x2a48ba6d,0x35c2b93a,0x36d7b81d,0x3a8aafd6,0x3b3b3add,0x389b3bf1,0x395f3bea,0x26483b25,0xb9ed30b2,0xbbffb732,
0x2e463ba8,0xa6483b99,0xbbf6b4a5,0xbbffb505,0xba2fbb0e,0xb848bbb6,0x3913b78b,0x3ac2b444,0x3bf634a5,0x3b50393a,0x2e463ba8,0xb67c3a0f,
0xb913378b,0xbbe2afd6,0xba2fbb0e,0xb179bbf1,0xb0b23b88,0xb4443b77,0xbbeab564,0xbbb6b5c2,0xb3c6bbfe,0x2cb5bbe2,0x3bc3aa48,0x3bfa3179,
0x38c43b3b,0x2fd63bff,0xba6d36d7,0xbbf12648,0xbaddb95f,0xb505bbce,0x381db9ed,0x3b99b303,0xb61f3b64,0xb7e33b50,0xbb64b61f,0xbaf6b67c,
0x361fbb64,0x393aba8a,0x3b64361f,0x3a0f389b,0xb61f3b64,0xba4f3984,0xbb64b61f,0xb8ecb9cb,0x361fbb64,0x3b25b848,0x3b64361f,0x37323ac2,
0xb8c43b3b,0xb9843b25,0xba6db6d7,0xb9cbb732,0x3addb95f,0x3bceb7e3,0x381d39ed,0x33033af6,0xbbea3564,0xbb77acb5,0xb0b2bb88,0x35c2bbfa,
0x3bc32a48,0x389b38ec,0xb3c63bfe,0xba8a3a4f,0xba2f3b0e,0xbac23af6,0xb913b78b,0xb848b7e3,0x3bf6b4a5,0x3b50acb5,0xae463ba8,0xb67c3bfa,
0xb913b78b,0xb179ba4f,0x3a2fbb0e,0x3be2b8ec,0xae463ba8,0xb9cb3b99,0xbbf634a5,0xb984b505,0xbb3b3add,0xbb993ac2,0xb6d7b81d,0xb505b848,
0x39ed30b2,0x37e335c2,0xb95f3bea,0xbaf63b77,0x3564bbc3,0x3a0fbbe2,0x3b88b3c6,0x393a3179,0xbbfe38c4,0xba4f2648,0xaa48ba6d,0x38ecbbff,
0xbbd93aa7,0xbbfa3a8a,0xb23eb872,0xacb5b89b,0x323e3872,0xafd639cb,0xbbd93aa7,0xbbf13984,0x3bd9baa7,0x3b99b848,0x323e3872,0xb5053ac2,
0xb23eb872,0x37e3bb77,0x3bd9baa7,0x3af6b5c2,0xbbfe3a6d,0xbbe23a4f,0x2a48b8c4,0x3179b8ec,0xb6d73add,0xb9843b99,0xbb3b381d,0xb9cb3505,
0x395fb0b2,0x33033444,0xb9ed3bea,0xbbce3bb6,0x3b88bbc3,0x3b77b93a,0x356433c6,0xb5c23a0f,0xbba83a2f,0xbb503a0f,0x34a5b913,0x367cb93a,
0xbb0e3bf6,0xbbe23bf1,0xb78b2e46,0xb179afd6,0xb4a53913,0xb9cb3b25,0xbba83a2f,0xb9843732,0x378bae46,0xb30337e3,0xbb0e3bf6,0xbbce3af6,
0xbadd39ed,0xba4f39cb,0x381db95f,0x38ecb984,0xbbea3b88,0xbb253ac2,0x30b2b564,0x3732b848,0xbbc33bfe,0xbbb63b77,0xb3c62a48,0x3444b5c2,
0xba6d3b3b,0xbbfa3be2,0xb8c436d7,0x2cb5b179,0xb9a839a8,0xb8ec3984,0x39a8b9a8,0x3a4fb9cb,0xb9a839a8,0xb7323848,0x39a8b9a8,0x3b25bac2,
0xb9a839a8,0xb44435c2,0x39a8b9a8,0x3bb6bb77,0xb9a839a8,0xacb53179,0x39a8b9a8,0x3bfabbe2,0xb81d395f,0xb67c393a,0x3addb9ed,0x3b50ba0f,
0xb0b23564,0x31792fd6,0x3beabb88,0x3be2bbf1,0x33c6aa48,0x3984b732,0x3bc3bbfe,0x39cbbb25,0x38c4b6d7,0x3bcebaf6,0x3a6dbb3b,0x3303b7e3,
0xb4a53913,0xb17938ec,0x3ba8ba2f,0x3be2ba4f,0x378bae46,0x39cbb505,0x3b0ebbf6,0x3984bb99,0x3ba8ba2f,0x3bcebbb6,0x34a5b913,0xb303b444,
0x3b0ebbf6,0x35c2ba0f,0xb78b2e46,0xbb77393a,0xaa4838c4,0x2cb5389b,0x3bfeba6d,0x3bfaba8a,0x3b3bb81d,0x3bf1b984,0x36d7badd,0x2fd6b9cb,
0x39edbbea,0x3505bac2,0xb95f30b2,0xbb993848,0xb564b3c6,0xbaf635c2,0xbb883bc3,0xb7e33b77,0x323e3872,0x35053848,0x3bd9baa7,0x3b99bac2,
0x3bd9baa7,0x3af6bb77,0xb23eb872,0xb7e3b5c2,0xb23eb872,0xb93ab179,0xbbd93aa7,0xba0f3be2,0xbbd93aa7,0xb8ec3bff,0x323e3872,0x3a4fa648,
0x36d7381d,0x384837e3,0x3b3bbadd,0x3ac2baf6,0x395fbbea,0x367cbbfa,0xb9edb0b2,0xbb502cb5,0xbb8833c6,0xbbe238ec,0xb5643bc3,0x31793a4f,
0x2a483a6d,0x39843505,0x3bfeb8c4,0x39cbbb99,0x3913378b,0x39cb3732,0x3a2fbb0e,0x3984bb25,0x2e46bba8,0xb303baf6,0xbbf634a5,0xbbce37e3,
0xba2f3b0e,0xb5c23bfa,0x3913378b,0x3b772cb5,0x3bf6b4a5,0x3a8aba4f,0x2e46bba8,0xb89bb8ec,0x3a6d36d7,0x3af6367c,0x38c4bb3b,0x37e3bb50,
0xb81db9ed,0xba0fb89b,0xbadd395f,0xb93a3a8a,0x30b23b88,0x38ec39cb,0x3beab564,0x3a4fb984,0x33c6bbfe,0xb732bac2,0xbbc3aa48,0xbb253848,
0x3b64361f,0x3bb635c2,0x361fbb64,0x3444bb77,0xbb64b61f,0xbbfab179,0xb61f3b64,0xacb53be2,0x3b64361f,0x3bf1a648,0x361fbb64,0xafd6bbff,
0xbb64b61f,0xbb993303,0xb61f3b64,0x35053bce,0x3bea3564,0x3bff3505,0x30b2bb88,0x2648bb99,0xbbc32a48,0xbac23444,0x33c63bfe,0x38483bb6,
0x3a6db6d7,0x367cba0f,0xb8c4bb3b,0xbb50b93a,0xb81d39ed,0x31793bf1,0x3add395f,0x3be22fd6,0x3bf634a5,0x3bce3444,0xae46bba8,0xb303bbb6,
0xb913378b,0xb5c2393a,0x3a2f3b0e,0x3b773a0f,0xae46bba8,0xb89bbbf1,0xbbf6b4a5,0xba8a2fd6,0x3a2f3b0e,0x3bff3732,0x3913b78b,0xa648bb25,
0x3b8833c6,0x3b253303,0xb564bbc3,0xb732bbce,0xaa483a6d,0x34443b50,0x3bfe38c4,0x3bb6367c,0xbb3bbadd,0xbbfab89b,0xb6d7381d,0x2cb53a8a,
0x39edb0b2,0x2fd6b984,0xb95fbbea,0xbbf1b9cb,0x3aa7323e,0x3a0f3179,0xb872bbd9,0xb93abbe2,0x38723bd9,0x3a4f3bff,0x3aa7323e,0x38eca648,
0xbaa7b23e,0xb7323303,0x38723bd9,0x3b253bce,0xb872bbd9,0xbbb6bb50,0xbaa7b23e,0xb444367c,0x395f30b2,0x389b2fd6,0xb9edbbea,0xba8abbf1,
0x3b883bc3,0x3bff3b25,0x3564b3c6,0x2648b732,0x2a4838c4,0x38483af6,0x3bfe3a6d,0x3ac237e3,0xbb3bb81d,0xb67c2cb5,0x36d73add,0x3b503bfa,
0x378b2e46,0x35c22cb5,0xbb0ebbf6,0xbb77bbfa,0x3ba83a2f,0x3a8a38ec,0xb4a5b913,0xb89bba4f,0x3b0e3bf6,0x3bff3b99,0x378b2e46,0xa648b505,
0x34a53913,0x3ac23bb6,0x3ba83a2f,0x38483444,0x33c62a48,0x2fd62648,0xbbc3bbfe,0xbbf1bbff,0x38c436d7,0x35053303,0xba6dbb3b,0xbb99bbce,
0x3add39ed,0x37e3367c,0xb81db95f,0xbaf6bb50,0x3bea3b88,0x393a389b,0xb0b2b564,0xba0fba8a,0x3c003c00,0xbbf1bbff,0,0x2fd62648,
0x3c003c00,0xbb99bbce,0,0x35053303,0x3c003c00,0xbaf6bb50,0,0x37e3367c,0x3c003c00,0xba0fba8a,0,0x393a389b,
0x3bc33bfe,0xbb77bbfa,0xb3c6aa48,0x35c22cb5,0x3a6d3b3b,0xb89bba4f,0xb8c4b6d7,0x3a8a38ec,0x381d395f,0xa648b505,0xbaddb9ed,0x3bff3b99,
0x30b23564,0x38483444,0xbbeabb88,0x3ac23bb6,0x3b0e3bf6,0xba8abbf1,0xb78bae46,0x389b2fd6,0x34a53913,0x2648b732,0xbba8ba2f,0x3bff3b25,
0xb78bae46,0x3ac237e3,0xbb0ebbf6,0x38483af6,0xbba8ba2f,0x3b503bfa,0xb4a5b913,0xb67c2cb5,0x39ed3bea,0xb93abbe2,0xb95fb0b2,0x3a0f3179,
0xb56433c6,0x38eca648,0xbb88bbc3,0x3a4f3bff,0xbbfeba6d,0x3b253bce,0xaa48b8c4,0xb7323303,0xb6d7badd,0xb444367c,0x3b3b381d,0xbbb6bb50,
0x38723bd9,0xb732bbce,0xbaa7b23e,0x3b253303,0xbaa7b23e,0x3bb6367c,0xb872bbd9,0x34443b50,0xb872bbd9,0x2cb53a8a,0x3aa7323e,0xbbfab89b,
0x3aa7323e,0xbbf1b9cb,0x38723bd9,0x2fd6b984,0x35643bc3,0xb303bbb6,0xbb88b3c6,0x3bce3444,0xbbfeb8c4,0x3b773a0f,0x2a48ba6d,0xb5c2393a,
0x36d7b81d,0xba8a2fd6,0x3b3b3add,0xb89bbbf1,0x395f3bea,0xa648bb25,0xb9ed30b2,0x3bff3732,0x2e463ba8,0x2648bb99,0xbbf6b4a5,0x3bff3505,
0xba2fbb0e,0x38483bb6,0x3913b78b,0xbac23444,0x3bf634a5,0xbb50b93a,0x2e463ba8,0x367cba0f,0xb913378b,0x3be22fd6,0xba2fbb0e,0x31793bf1,
0xb0b23b88,0x3444bb77,0xbbeab564,0x3bb635c2,0xb3c6bbfe,0xacb53be2,0x3bc3aa48,0xbbfab179,0x38c43b3b,0xafd6bbff,0xba6d36d7,0x3bf1a648,
0xbaddb95f,0x35053bce,0x381db9ed,0xbb993303,0xb61f3b64,0x37e3bb50,0xbb64b61f,0x3af6367c,0x361fbb64,0xb93a3a8a,0x3b64361f,0xba0fb89b,
0xb61f3b64,0x3a4fb984,0xbb64b61f,0x38ec39cb,0x361fbb64,0xbb253848,0x3b64361f,0xb732bac2,0xb8c43b3b,0x3984bb25,0xba6db6d7,0x39cb3732,
0x3addb95f,0xbbce37e3,0x381d39ed,0xb303baf6,0xbbea3564,0x3b772cb5,0xb0b2bb88,0xb5c23bfa,0x3bc32a48,0xb89bb8ec,0xb3c63bfe,0x3a8aba4f,
0xba2f3b0e,0x3ac2baf6,0xb913b78b,0x384837e3,0x3bf6b4a5,0xbb502cb5,0xae463ba8,0x367cbbfa,0xb913b78b,0x31793a4f,0x3a2fbb0e,0xbbe238ec,
0xae463ba8,0x39cbbb99,0xbbf634a5,0x39843505,0xbb3b3add,0x3b99bac2,0xb6d7b81d,0x35053848,0x39ed30b2,0xb7e3b5c2,0xb95f3bea,0x3af6bb77,
0x3564bbc3,0xba0f3be2,0x3b88b3c6,0xb93ab179,0xbbfe38c4,0x3a4fa648,0xaa48ba6d,0xb8ec3bff,0xbbd93aa7,0x3bfaba8a,0xb23eb872,0x2cb5389b,
0x323e3872,0x2fd6b9cb,0xbbd93aa7,0x3bf1b984,0x3bd9baa7,0xbb993848,0x323e3872,0x3505bac2,0xb23eb872,0xb7e33b77,0x3bd9baa7,0xbaf635c2,
0xbbfe3a6d,0x3be2ba4f,0x2a48b8c4,0xb17938ec,0xb6d73add,0x3984bb99,0xbb3b381d,0x39cbb505,0x395fb0b2,0xb303b444,0xb9ed3bea,0x3bcebbb6,
0x3b88bbc3,0xbb77393a,0x356433c6,0x35c2ba0f,0xbba83a2f,0x3b50ba0f,0x34a5b913,0xb67c393a,0xbb0e3bf6,0x3be2bbf1,0xb78b2e46,0x31792fd6,
0xb4a53913,0x39cbbb25,0xbba83a2f,0x3984b732,0x378bae46,0x3303b7e3,0xbb0e3bf6,0x3bcebaf6,0xbadd39ed,0x3a4fb9cb,0x381db95f,0xb8ec3984,
0xbbea3b88,0x3b25bac2,0x30b2b564,0xb7323848,0xbbc33bfe,0x3bb6bb77,0xb3c62a48,0xb44435c2,0xba6d3b3b,0x3bfabbe2,0xb8c436d7,0xacb53179,
0xb9a839a8,0x38ecb984,0x39a8b9a8,0xba4f39cb,0xb9a839a8,0x3732b848,0x39a8b9a8,0xbb253ac2,0xb9a839a8,0x3444b5c2,0x39a8b9a8,0xbbb63b77,
0xb9a839a8,0x2cb5b179,0x39a8b9a8,0xbbfa3be2,0xb81d395f,0x367cb93a,0x3addb9ed,0xbb503a0f,0xb0b23564,0xb179afd6,0x3beabb88,0xbbe23bf1,
0x33c6aa48,0xb9843732,0x3bc3bbfe,0xb9cb3b25,0x38c4b6d7,0xbbce3af6,0x3a6dbb3b,0xb30337e3,0xb4a53913,0x3179b8ec,0x3ba8ba2f,0xbbe23a4f,
0x378bae46,0xb9cb3505,0x3b0ebbf6,0xb9843b99,0x3ba8ba2f,0xbbce3bb6,0x34a5b913,0x33033444,0x3b0ebbf6,0xb5c23a0f,0xb78b2e46,0x3b77b93a,
0xaa4838c4,0xacb5b89b,0x3bfeba6d,0xbbfa3a8a,0x3b3bb81d,0xbbf13984,0x36d7badd,0xafd639cb,0x39edbbea,0xb5053ac2,0xb95f30b2,0x3b99b848,
0xb564b3c6,0x3af6b5c2,0xbb883bc3,0x37e3bb77,0x323e3872,0xb505b848,0x3bd9baa7,0xbb993ac2,0x3bd9baa7,0xbaf63b77,0xb23eb872,0x37e335c2,
0xb23eb872,0x393a3179,0xbbd93aa7,0x3a0fbbe2,0xbbd93aa7,0x38ecbbff,0x323e3872,0xba4f2648,0x36d7381d,0xb848b7e3,0x3b3bbadd,0xbac23af6,
0x395fbbea,0xb67c3bfa,0xb9edb0b2,0x3b50acb5,0xbb8833c6,0x3be2b8ec,0xb5643bc3,0xb179ba4f,0x2a483a6d,0xb984b505,0x3bfeb8c4,0xb9cb3b99,
0x3913378b,0xb9cbb732,0x3a2fbb0e,0xb9843b25,0x2e46bba8,0x33033af6,0xbbf634a5,0x3bceb7e3,0xba2f3b0e,0x35c2bbfa,0x3913378b,0xbb77acb5,
0x3bf6b4a5,0xba8a3a4f,0x2e46bba8,0x389b38ec,0x3a6d36d7,0xbaf6b67c,0x38c4bb3b,0xb7e33b50,0xb81db9ed,0x3a0f389b,0xbadd395f,0x393aba8a,
0x30b23b88,0xb8ecb9cb,0x3beab564,0xba4f3984,0x33c6bbfe,0x37323ac2,0xbbc3aa48,0x3b25b848,0x3b64361f,0xbbb6b5c2,0x361fbb64,0xb4443b77,
0xbb64b61f,0x3bfa3179,0xb61f3b64,0x2cb5bbe2,0x3b64361f,0xbbf12648,0x361fbb64,0x2fd63bff,0xbb64b61f,0x3b99b303,0xb61f3b64,0xb505bbce,
0x3bea3564,0xbbffb505,0x30b2bb88,0xa6483b99,0xbbc32a48,0x3ac2b444,0x33c63bfe,0xb848bbb6,0x3a6db6d7,0xb67c3a0f,0xb8c4bb3b,0x3b50393a,
0xb81d39ed,0xb179bbf1,0x3add395f,0xbbe2afd6,0x3bf634a5,0xbbceb444,0xae46bba8,0x33033bb6,0xb913378b,0x35c2b93a,0x3a2f3b0e,0xbb77ba0f,
0xae46bba8,0x389b3bf1,0xbbf6b4a5,0x3a8aafd6,0x3a2f3b0e,0xbbffb732,0x3913b78b,0x26483b25,0x3b8833c6,0xbb25b303,0xb564bbc3,0x37323bce,
0xaa483a6d,0xb444bb50,0x3bfe38c4,0xbbb6b67c,0xbb3bbadd,0x3bfa389b,0xb6d7381d,0xacb5ba8a,0x39edb0b2,0xafd63984,0xb95fbbea,0x3bf139cb,
0x3aa7323e,0xba0fb179,0xb872bbd9,0x393a3be2,0x38723bd9,0xba4fbbff,0x3aa7323e,0xb8ec2648,0xbaa7b23e,0x3732b303,0x38723bd9,0xbb25bbce,
0xb872bbd9,0x3bb63b50,0xbaa7b23e,0x3444b67c,0x395f30b2,0xb89bafd6,0xb9edbbea,0x3a8a3bf1,0x3b883bc3,0xbbffbb25,0x3564b3c6,0xa6483732,
0x2a4838c4,0xb848baf6,0x3bfe3a6d,0xbac2b7e3,0xbb3bb81d,0x367cacb5,0x36d73add,0xbb50bbfa,0x378b2e46,0xb5c2acb5,0xbb0ebbf6,0x3b773bfa,
0x3ba83a2f,0xba8ab8ec,0xb4a5b913,0x389b3a4f,0x3b0e3bf6,0xbbffbb99,0x378b2e46,0x26483505,0x34a53913,0xbac2bbb6,0x3ba83a2f,0xb848b444,
0x33c62a48,0xafd6a648,0xbbc3bbfe,0x3bf13bff,0x38c436d7,0xb505b303,0xba6dbb3b,0x3b993bce,0x3add39ed,0xb7e3b67c,0xb81db95f,0x3af63b50,
0x3bea3b88,0xb93ab89b,0xb0b2b564,0x3a0f3a8a,0x3c003c00,0x38ec3984,0,0xba4fb9cb,0x3c003c00,0x37323848,0,0xbb25bac2,
0x3c003c00,0x344435c2,0,0xbbb6bb77,0x3c003c00,0x2cb53179,0,0xbbfabbe2,0xb3c6aa48,0xbb50ba0f,0xbbc3bbfe,0xb67cb93a,
0xb8c4b6d7,0xbbe2bbf1,0xba6dbb3b,0x3179afd6,0xbaddb9ed,0xb9cbbb25,0xb81db95f,0x39843732,0xbbeabb88,0xb303b7e3,0xb0b2b564,0x3bce3af6,
0xbb0ebbf6,0xb179b8ec,0x378b2e46,0x3be23a4f,0xb4a5b913,0x39cb3505,0x3ba83a2f,0x39843b99,0x378b2e46,0x3bce3bb6,0x3b0e3bf6,0xb3033444,
0x3ba83a2f,0x35c23a0f,0x34a53913,0xbb77b93a,0x395f30b2,0x3bfa3a8a,0x39ed3bea,0xacb5389b,0x3b883bc3,0x2fd639cb,0xb56433c6,0xbbf1b984,
0x2a4838c4,0xbb99b848,0xbbfeba6d,0xb505bac2,0xbb3bb81d,0xb7e3bb77,0xb6d7badd,0x3af635c2,0x38723bd9,0xb5053848,0xbaa7b23e,0xbb99bac2,
0xbaa7b23e,0xbaf6bb77,0xb872bbd9,0x37e3b5c2,0xb872bbd9,0x393ab179,0x3aa7323e,0x3a0f3be2,0x3aa7323e,0x38ec3bff,0x38723bd9,0xba4fa648,
0xbb88b3c6,0xbac2baf6,0xb564bbc3,0x3848b7e3,0x2a48ba6d,0x3b502cb5,0x3bfe38c4,0x367c3bfa,0x3b3b3add,0xb1793a4f,0xb6d7381d,0xbbe2b8ec,
0xb9ed30b2,0xb9cbbb99,0xb95fbbea,0x3984b505,0xae46bba8,0x39cbb732,0x3bf634a5,0x39843b25,0x3a2f3b0e,0xb3033af6,0xb913378b,0xbbceb7e3,
0xbbf6b4a5,0xb5c2bbfa,0xae46bba8,0x3b77acb5,0x3913b78b,0x3a8a3a4f,0x3a2f3b0e,0xb89b38ec,0x3bea3564,0x37e33b50,0xb0b23b88,0xbaf6367c,
0xbbc32a48,0xb93aba8a,0xb3c6bbfe,0x3a0fb89b,0x3a6db6d7,0x3a4f3984,0x38c43b3b,0xb8ec39cb,0xb81d39ed,0xbb25b848,0xbaddb95f,0x3732bac2,
0xb61f3b64,0xbbb635c2,0xbb64b61f,0xb444bb77,0x361fbb64,0x3bfab179,0x3b64361f,0x2cb53be2,0xb61f3b64,0xbbf1a648,0xbb64b61f,0x2fd6bbff,
0x361fbb64,0x3b993303,0x3b64361f,0xb5053bce,0xba6db6d7,0xa648bb99,0x38c4bb3b,0x3bffb505,0x381d39ed,0xb8483bb6,0xbadd395f,0xbac2b444,
0xb0b2bb88,0x3b50b93a,0x3beab564,0x367c3a0f,0xb3c63bfe,0xbbe22fd6,0xbbc3aa48,0x3179bbf1,0x3a2fbb0e,0x3bceb444,0x3913378b,0xb3033bb6,
0xbbf634a5,0xb5c2b93a,0x2e46bba8,0x3b77ba0f,0x3913378b,0xb89b3bf1,0xba2f3b0e,0xba8aafd6,0x2e46bba8,0x3bffb732,0x3bf6b4a5,0xa6483b25,
0x36d7381d,0xb7323bce,0xbb3b3add,0xbb253303,0x395fbbea,0x3bb6b67c,0x39ed30b2,0xb4443b50,0xbb8833c6,0x2cb5ba8a,0x3564bbc3,0x3bfab89b,
0x2a483a6d,0xbbf139cb,0xbbfe38c4,0xafd6b984,0xbbd93aa7,0xba0f3179,0xb23eb872,0x393abbe2,0x323e3872,0xba4f3bff,0xbbd93aa7,0xb8eca648,
0x3bd9baa7,0x37323303,0x323e3872,0xbb253bce,0xb23eb872,0x3bb6bb50,0x3bd9baa7,0x3444367c,0x2a48b8c4,0x3a8abbf1,0x3bfeba6d,0x389bafd6,
0xbb3b381d,0xa648b732,0x36d7badd,0x3bffbb25,0xb9ed3bea,0xbac237e3,0xb95f30b2,0x3848baf6,0x356433c6,0xbb503bfa,0xbb883bc3,0xb67cacb5,
0x3ba8ba2f,0x35c2acb5,0xb4a53913,0xbb773bfa,0x3b0ebbf6,0x3a8ab8ec,0x378bae46,0xb89b3a4f,0x34a5b913,0x3bffbb99,0x3ba8ba2f,0xa6483505,
0xb78b2e46,0x3ac2bbb6,0x3b0ebbf6,0x3848b444,0xb81d395f,0xbbf13bff,0xbadd39ed,0xafd62648,0xb0b23564,0xbb993bce,0xbbea3b88,0xb5053303,
0x33c6aa48,0xbaf63b50,0xbbc33bfe,0xb7e3367c,0x38c4b6d7,0xba0f3a8a,0xba6d3b3b,0xb93a389b,0xb9a839a8,0x2fd6a648,0x39a8b9a8,0x3bf1bbff,
0xb9a839a8,0x3505b303,0x39a8b9a8,0x3b99bbce,0xb9a839a8,0x37e3b67c,0x39a8b9a8,0x3af6bb50,0xb9a839a8,0x393ab89b,0x39a8b9a8,0x3a0fba8a,
0x3addb9ed,0x3b77bbfa,0x381db95f,0xb5c22cb5,0x3beabb88,0x389bba4f,0x30b2b564,0xba8a38ec,0x3bc3bbfe,0x2648b505,0xb3c62a48,0xbbff3b99,
0x3a6dbb3b,0xb8483444,0xb8c436d7,0xbac23bb6,0x34a5b913,0xb89b2fd6,0xbba83a2f,0xba8a3bf1,0xb78b2e46,0xbbff3b25,0xbb0e3bf6,0x26483732,
0xbba83a2f,0xb8483af6,0xb4a53913,0x3ac2b7e3,0xbb0e3bf6,0x367c2cb5,0x378bae46,0x3b50bbfa,0xbbfe3a6d,0xb93a3be2,0xaa4838c4,0x3a0fb179,
0xb6d73add,0x38ec2648,0x3b3bb81d,0x3a4fbbff,0x395fb0b2,0x3b25bbce,0x39edbbea,0xb732b303,0x3b88bbc3,0xb444b67c,0xb564b3c6,0xbbb63b50,
0x323e3872,0x3b25b303,0x3bd9baa7,0x3732bbce,0x3bd9baa7,0x3444bb50,0xb23eb872,0xbbb6367c,0xb23eb872,0xbbfa389b,0xbbd93aa7,0xacb53a8a,
0xbbd93aa7,0x2fd63984,0x323e3872,0x3bf1b9cb,0x3b3bbadd,0x3303bbb6,0xb6d7b81d,0xbbce3444,0xb9edb0b2,0xbb773a0f,0xb95f3bea,0x35c2393a,
0xb5643bc3,0x3a8a2fd6,0x3b88b3c6,0x389bbbf1,0x3bfeb8c4,0x2648bb25,0xaa48ba6d,0xbbff3732,0xb913b78b,0xbbff3505,0xba2f3b0e,0x26483b99,
0xae463ba8,0x3ac23444,0x3bf6b4a5,0x3848bbb6,0x3a2fbb0e,0xb67cba0f,0xb913b78b,0xbb50393a,0xbbf634a5,0xb1793bf1,0xae463ba8,0x3be2afd6,
0xb8c43b3b,0x34443b77,0x3a6d36d7,0x3bb6b5c2,0x3addb95f,0xacb5bbe2,0xb81db9ed,0xbbfa3179,0xbbea3564,0xafd63bff,0x30b23b88,0x3bf12648,
0x3bc32a48,0x3505bbce,0x33c6bbfe,0xbb99b303,0x3b64361f,0x3af6b67c,0x361fbb64,0xb7e3bb50,0xbb64b61f,0xba0f389b,0xb61f3b64,0x393a3a8a,
0x3b64361f,0x38ecb9cb,0x361fbb64,0xba4fb984,0xbb64b61f,0xb7323ac2,0xb61f3b64,0x3b253848,0x30b2bb88,0xb984bb25,0xbbeab564,0xb9cb3732,
0x33c63bfe,0x3bce37e3,0x3bc3aa48,0x3303baf6,0xb8c4bb3b,0xbb772cb5,0xba6d36d7,0x35c23bfa,0x3add395f,0x389bb8ec,0x381db9ed,0xba8aba4f,
0xbbf6b4a5,0xb84837e3,0x2e463ba8,0x3ac23af6,0x3913b78b,0xb67cbbfa,0xba2fbb0e,0xbb50acb5,0x2e463ba8,0x3be238ec,0x3bf634a5,0x3179ba4f,
0xba2fbb0e,0xb9843505,0xb913378b,0x39cb3b99,0x35643bc3,0x3b993ac2,0x3b8833c6,0x3505b848,0xbbfeb8c4,0xb7e335c2,0xaa483a6d,0x3af63b77,
0x36d7b81d,0xba0fbbe2,0xbb3bbadd,0xb93a3179,0x395f3bea,0x3a4f2648,0x39edb0b2,0xb8ecbbff,0x3aa7323e,0x2cb5b89b,0xb872bbd9,0xbbfaba8a,
0x38723bd9,0x3bf13984,0x3aa7323e,0xafd6b9cb,0xbaa7b23e,0x35053ac2,0x38723bd9,0x3b993848,0xb872bbd9,0xbaf6b5c2,0xbaa7b23e,0x37e33b77,
0xb9edbbea,0xbbe2ba4f,0xb95fb0b2,0x317938ec,0x3564b3c6,0xb984bb99,0xbb88bbc3,0xb9cbb505,0x3bfe3a6d,0x3303b444,0xaa48b8c4,0xbbcebbb6,
0x36d73add,0x3b77393a,0x3b3b381d,0xb5c2ba0f,0xb78bae46,0x367c393a,0x3b0e3bf6,0x3b503a0f,0xbba8ba2f,0xb1792fd6,0x34a53913,0x3be23bf1,
0xbb0ebbf6,0xb984b732,0xb78bae46,0x39cb3b25,0xb4a5b913,0xbbcebaf6,0xbba8ba2f,0x330337e3,0x3bc33bfe,0x3a4f39cb,0x33c62a48,0xb8ecb984,
0x3a6d3b3b,0x3b253ac2,0x38c436d7,0xb732b848,0x381d395f,0x3bb63b77,0x3add39ed,0xb444b5c2,0x30b23564,0x3bfa3be2,0x3bea3b88,0xacb5b179,
0x3c003c00,0xb8ecb984,0,0x3a4f39cb,0x3c003c00,0xb732b848,0,0x3b253ac2,0x3c003c00,0xb444b5c2,0,0x3bb63b77,
0x3c003c00,0xacb5b179,0,0x3bfa3be2,0xb3c6aa48,0x3b503a0f,0xbbc3bbfe,0x367c393a,0xb8c4b6d7,0x3be23bf1,0xba6dbb3b,0xb1792fd6,
0xbaddb9ed,0x39cb3b25,0xb81db95f,0xb984b732,0xbbeabb88,0x330337e3,0xb0b2b564,0xbbcebaf6,0xbb0ebbf6,0x317938ec,0x378b2e46,0xbbe2ba4f,
0xb4a5b913,0xb9cbb505,0x3ba83a2f,0xb984bb99,0x378b2e46,0xbbcebbb6,0x3b0e3bf6,0x3303b444,0x3ba83a2f,0xb5c2ba0f,0x34a53913,0x3b77393a,
0x395f30b2,0xbbfaba8a,0x39ed3bea,0x2cb5b89b,0x3b883bc3,0xafd6b9cb,0xb56433c6,0x3bf13984,0x2a4838c4,0x3b993848,0xbbfeba6d,0x35053ac2,
0xbb3bb81d,0x37e33b77,0xb6d7badd,0xbaf6b5c2,0x38723bd9,0x3505b848,0xbaa7b23e,0x3b993ac2,0xbaa7b23e,0x3af63b77,0xb872bbd9,0xb7e335c2,
0xb872bbd9,0xb93a3179,0x3aa7323e,0xba0fbbe2,0x3aa7323e,0xb8ecbbff,0x38723bd9,0x3a4f2648,0xbb88b3c6,0x3ac23af6,0xb564bbc3,0xb84837e3,
0x2a48ba6d,0xbb50acb5,0x3bfe38c4,0xb67cbbfa,0x3b3b3add,0x3179ba4f,0xb6d7381d,0x3be238ec,0xb9ed30b2,0x39cb3b99,0xb95fbbea,0xb9843505,
0xae46bba8,0xb9cb3732,0x3bf634a5,0xb984bb25,0x3a2f3b0e,0x3303baf6,0xb913378b,0x3bce37e3,0xbbf6b4a5,0x35c23bfa,0xae46bba8,0xbb772cb5,
0x3913b78b,0xba8aba4f,0x3a2f3b0e,0x389bb8ec,0x3bea3564,0xb7e3bb50,0xb0b23b88,0x3af6b67c,0xbbc32a48,0x393a3a8a,0xb3c6bbfe,0xba0f389b,
0x3a6db6d7,0xba4fb984,0x38c43b3b,0x38ecb9cb,0xb81d39ed,0x3b253848,0xbaddb95f,0xb7323ac2,0xb61f3b64,0x3bb6b5c2,0xbb64b61f,0x34443b77,
0x361fbb64,0xbbfa3179,0x3b64361f,0xacb5bbe2,0xb61f3b64,0x3bf12648,0xbb64b61f,0xafd63bff,0x361fbb64,0xbb99b303,0x3b64361f,0x3505bbce,
0xba6db6d7,0x26483b99,0x38c4bb3b,0xbbff3505,0x381d39ed,0x3848bbb6,0xbadd395f,0x3ac23444,0xb0b2bb88,0xbb50393a,0x3beab564,0xb67cba0f,
0xb3c63bfe,0x3be2afd6,0xbbc3aa48,0xb1793bf1,0x3a2fbb0e,0xbbce3444,0x3913378b,0x3303bbb6,0xbbf634a5,0x35c2393a,0x2e46bba8,0xbb773a0f,
0x3913378b,0x389bbbf1,0xba2f3b0e,0x3a8a2fd6,0x2e46bba8,0xbbff3732,0x3bf6b4a5,0x2648bb25,0x36d7381d,0x3732bbce,0xbb3b3add,0x3b25b303,
0x395fbbea,0xbbb6367c,0x39ed30b2,0x3444bb50,0xbb8833c6,0xacb53a8a,0x3564bbc3,0xbbfa389b,0x2a483a6d,0x3bf1b9cb,0xbbfe38c4,0x2fd63984,
0xbbd93aa7,0x3a0fb179,0xb23eb872,0xb93a3be2,0x323e3872,0x3a4fbbff,0xbbd93aa7,0x38ec2648,0x3bd9baa7,0xb732b303,0x323e3872,0x3b25bbce,
0xb23eb872,0xbbb63b50,0x3bd9baa7,0xb444b67c,0x2a48b8c4,0xba8a3bf1,0x3bfeba6d,0xb89b2fd6,0xbb3b381d,0x26483732,0x36d7badd,0xbbff3b25,
0xb9ed3bea,0x3ac2b7e3,0xb95f30b2,0xb8483af6,0x356433c6,0x3b50bbfa,0xbb883bc3,0x367c2cb5,0x3ba8ba2f,0xb5c22cb5,0xb4a53913,0x3b77bbfa,
0x3b0ebbf6,0xba8a38ec,0x378bae46,0x389bba4f,0x34a5b913,0xbbff3b99,0x3ba8ba2f,0x2648b505,0xb78b2e46,0xbac23bb6,0x3b0ebbf6,0xb8483444,
0xb81d395f,0x3bf1bbff,0xbadd39ed,0x2fd6a648,0xb0b23564,0x3b99bbce,0xbbea3b88,0x3505b303,0x33c6aa48,0x3af6bb50,0xbbc33bfe,0x37e3b67c,
0x38c4b6d7,0x3a0fba8a,0xba6d3b3b,0x393ab89b,0xb9a839a8,0xafd62648,0x39a8b9a8,0xbbf13bff,0xb9a839a8,0xb5053303,0x39a8b9a8,0xbb993bce,
0xb9a839a8,0xb7e3367c,0x39a8b9a8,0xbaf63b50,0xb9a839a8,0xb93a389b,0x39a8b9a8,0xba0f3a8a,0x3addb9ed,0xbb773bfa,0x381db95f,0x35c2acb5,
0x3beabb88,0xb89b3a4f,0x30b2b564,0x3a8ab8ec,0x3bc3bbfe,0xa6483505,0xb3c62a48,0x3bffbb99,0x3a6dbb3b,0x3848b444,0xb8c436d7,0x3ac2bbb6,
0x34a5b913,0x389bafd6,0xbba83a2f,0x3a8abbf1,0xb78b2e46,0x3bffbb25,0xbb0e3bf6,0xa648b732,0xbba83a2f,0x3848baf6,0xb4a53913,0xbac237e3,
0xbb0e3bf6,0xb67cacb5,0x378bae46,0xbb503bfa,0xbbfe3a6d,0x393abbe2,0xaa4838c4,0xba0f3179,0xb6d73add,0xb8eca648,0x3b3bb81d,0xba4f3bff,
0x395fb0b2,0xbb253bce,0x39edbbea,0x37323303,0x3b88bbc3,0x3444367c,0xb564b3c6,0x3bb6bb50,0x323e3872,0xbb253303,0x3bd9baa7,0xb7323bce,
0x3bd9baa7,0xb4443b50,0xb23eb872,0x3bb6b67c,0xb23eb872,0x3bfab89b,0xbbd93aa7,0x2cb5ba8a,0xbbd93aa7,0xafd6b984,0x323e3872,0xbbf139cb,
0x3b3bbadd,0xb3033bb6,0xb6d7b81d,0x3bceb444,0xb9edb0b2,0x3b77ba0f,0xb95f3bea,0xb5c2b93a,0xb5643bc3,0xba8aafd6,0x3b88b3c6,0xb89b3bf1,
0x3bfeb8c4,0xa6483b25,0xaa48ba6d,0x3bffb732,0xb913b78b,0x3bffb505,0xba2f3b0e,0xa648bb99,0xae463ba8,0xbac2b444,0x3bf6b4a5,0xb8483bb6,
0x3a2fbb0e,0x367c3a0f,0xb913b78b,0x3b50b93a,0xbbf634a5,0x3179bbf1,0xae463ba8,0xbbe22fd6,0xb8c43b3b,0xb444bb77,0x3a6d36d7,0xbbb635c2,
0x3addb95f,0x2cb53be2,0xb81db9ed,0x3bfab179,0xbbea3564,0x2fd6bbff,0x30b23b88,0xbbf1a648,0x3bc32a48,0xb5053bce,0x33c6bbfe,0x3b993303,
0x3b64361f,0xbaf6367c,0x361fbb64,0x37e33b50,0xbb64b61f,0x3a0fb89b,0xb61f3b64,0xb93aba8a,0x3b64361f,0xb8ec39cb,0x361fbb64,0x3a4f3984,
0xbb64b61f,0x3732bac2,0xb61f3b64,0xbb25b848,0x30b2bb88,0x39843b25,0xbbeab564,0x39cbb732,0x33c63bfe,0xbbceb7e3,0x3bc3aa48,0xb3033af6,
0xb8c4bb3b,0x3b77acb5,0xba6d36d7,0xb5c2bbfa,0x3add395f,0xb89b38ec,0x381db9ed,0x3a8a3a4f,0xbbf6b4a5,0x3848b7e3,0x2e463ba8,0xbac2baf6,
0x3913b78b,0x367c3bfa,0xba2fbb0e,0x3b502cb5,0x2e463ba8,0xbbe2b8ec,0x3bf634a5,0xb1793a4f,0xba2fbb0e,0x3984b505,0xb913378b,0xb9cbbb99,
0x35643bc3,0xbb99bac2,0x3b8833c6,0xb5053848,0xbbfeb8c4,0x37e3b5c2,0xaa483a6d,0xbaf6bb77,0x36d7b81d,0x3a0f3be2,0xbb3bbadd,0x393ab179,
0x395f3bea,0xba4fa648,0x39edb0b2,0x38ec3bff,0x3aa7323e,0xacb5389b,0xb872bbd9,0x3bfa3a8a,0x38723bd9,0xbbf1b984,0x3aa7323e,0x2fd639cb,
0xbaa7b23e,0xb505bac2,0x38723bd9,0xbb99b848,0xb872bbd9,0x3af635c2,0xbaa7b23e,0xb7e3bb77,0xb9edbbea,0x3be23a4f,0xb95fb0b2,0xb179b8ec,
0x3564b3c6,0x39843b99,0xbb88bbc3,0x39cb3505,0x3bfe3a6d,0xb3033444,0xaa48b8c4,0x3bce3bb6,0x36d73add,0xbb77b93a,0x3b3b381d,0x35c23a0f,
0xb78bae46,0xb67cb93a,0x3b0e3bf6,0xbb50ba0f,0xbba8ba2f,0x3179afd6,0x34a53913,0xbbe2bbf1,0xbb0ebbf6,0x39843732,0xb78bae46,0xb9cbbb25,
0xb4a5b913,0x3bce3af6,0xbba8ba2f,0xb303b7e3,0x3bc33bfe,0xba4fb9cb,0x33c62a48,0x38ec3984,0x3a6d3b3b,0xbb25bac2,0x38c436d7,0x37323848,
0x381d395f,0xbbb6bb77,0x3add39ed,0x344435c2,0x30b23564,0xbbfabbe2,0x3bea3b88,0x2cb53179,0x3c003c00,0xafd6a648,0,0xbbf1bbff,
0x3c003c00,0xb505b303,0,0xbb99bbce,0x3c003c00,0xb7e3b67c,0,0xbaf6bb50,0x3c003c00,0xb93ab89b,0,0xba0fba8a,
0xbbc3bbfe,0x35c22cb5,0x33c62a48,0x3b773bfa,0xba6dbb3b,0x3a8a38ec,0x38c436d7,0x389b3a4f,0xb81db95f,0x3bff3b99,0x3add39ed,0x26483505,
0xb0b2b564,0x3ac23bb6,0x3bea3b88,0xb848b444,0x3b0e3bf6,0xb89bafd6,0xb78bae46,0xba8abbf1,0x34a53913,0xbbffbb25,0xbba8ba2f,0x2648b732,
0xb78bae46,0xb848baf6,0xbb0ebbf6,0x3ac237e3,0xbba8ba2f,0x367cacb5,0xb4a5b913,0x3b503bfa,0xb9edbbea,0x3a0f3179,0x395f30b2,0x393a3be2,
0x3564b3c6,0x3a4f3bff,0x3b883bc3,0xb8ec2648,0x3bfe3a6d,0xb7323303,0x2a4838c4,0xbb25bbce,0x36d73add,0xbbb6bb50,0xbb3bb81d,0x3444b67c,
0x38723bd9,0xbb25b303,0xbaa7b23e,0xb732bbce,0xbaa7b23e,0xb444bb50,0xb872bbd9,0x3bb6367c,0xb872bbd9,0x3bfa389b,0x3aa7323e,0x2cb53a8a,
0x3aa7323e,0xafd63984,0x38723bd9,0xbbf1b9cb,0xb564bbc3,0x3bce3444,0x3b8833c6,0x33033bb6,0x3bfe38c4,0xb5c2393a,0xaa483a6d,0xbb77ba0f,
0xb6d7381d,0xb89bbbf1,0xbb3bbadd,0x3a8aafd6,0xb95fbbea,0x3bff3732,0x39edb0b2,0x26483b25,0x2e463ba8,0xbbffb505,0xbbf6b4a5,0x2648bb99,
0xba2fbb0e,0x3ac2b444,0x3913b78b,0x38483bb6,0x3bf634a5,0xb67c3a0f,0x2e463ba8,0xbb50b93a,0xb913378b,0xb179bbf1,0xba2fbb0e,0x3be22fd6,
0x30b2bb88,0x3bb635c2,0x3bea3564,0xb4443b77,0x33c63bfe,0xbbfab179,0xbbc32a48,0x2cb5bbe2,0xb8c4bb3b,0x3bf1a648,0x3a6db6d7,0x2fd63bff,
0x3add395f,0xbb993303,0xb81d39ed,0xb505bbce,0xb61f3b64,0xbaf6b67c,0xbb64b61f,0x37e3bb50,0x361fbb64,0x3a0f389b,0x3b64361f,0xb93a3a8a,
0xb61f3b64,0xb8ecb9cb,0xbb64b61f,0x3a4fb984,0x361fbb64,0x37323ac2,0x3b64361f,0xbb253848,0x38c4bb3b,0x39cb3732,0x3a6d36d7,0xb9843b25,
0xbadd395f,0xb303baf6,0xb81db9ed,0x3bceb7e3,0x3beab564,0xb5c23bfa,0x30b23b88,0xbb77acb5,0xbbc3aa48,0x3a8aba4f,0x33c6bbfe,0x389b38ec,
0xba2f3b0e,0xb848b7e3,0xb913b78b,0x3ac2baf6,0x3bf6b4a5,0xb67c3bfa,0xae463ba8,0xbb502cb5,0xb913b78b,0x3be2b8ec,0x3a2fbb0e,0x31793a4f,
0xae463ba8,0xb984b505,0xbbf634a5,0x39cbbb99,0x3b3bbadd,0x35053848,0x36d7381d,0xbb993ac2,0xb9edb0b2,0x3af6bb77,0x395fbbea,0x37e335c2,
0xb5643bc3,0xb93ab179,0xbb8833c6,0x3a0fbbe2,0x3bfeb8c4,0xb8ec3bff,0x2a483a6d,0xba4f2648,0xbbd93aa7,0xacb5b89b,0xb23eb872,0x3bfaba8a,
0x323e3872,0xbbf13984,0xbbd93aa7,0x2fd6b9cb,0x3bd9baa7,0xb5053ac2,0x323e3872,0xbb993848,0xb23eb872,0x3af6b5c2,0x3bd9baa7,0xb7e33b77,
0x3bfeba6d,0xb17938ec,0xaa4838c4,0xbbe23a4f,0x36d7badd,0x39cbb505,0x3b3bb81d,0xb9843b99,0xb95f30b2,0x3bcebbb6,0x39edbbea,0x33033444,
0xbb883bc3,0x35c2ba0f,0xb564b3c6,0x3b77b93a,0xbba83a2f,0x367cb93a,0x34a5b913,0x3b50ba0f,0xbb0e3bf6,0xb179afd6,0xb78b2e46,0x3be2bbf1,
0xb4a53913,0xb9843732,0xbba83a2f,0x39cbbb25,0x378bae46,0xbbce3af6,0xbb0e3bf6,0x3303b7e3,0x3addb9ed,0xb8ec3984,0xb81d395f,0xba4f39cb,
0x3beabb88,0xb7323848,0xb0b23564,0xbb253ac2,0x3bc3bbfe,0xb44435c2,0x33c6aa48,0xbbb63b77,0x3a6dbb3b,0xacb53179,0x38c4b6d7,0xbbfa3be2,
0xb9a839a8,0x3a4fb9cb,0x39a8b9a8,0x38ecb984,0xb9a839a8,0x3b25bac2,0x39a8b9a8,0x3732b848,0xb9a839a8,0x3bb6bb77,0x39a8b9a8,0x3444b5c2,
0xb9a839a8,0x3bfabbe2,0x39a8b9a8,0x2cb5b179,0x381db95f,0xbb503a0f,0xbadd39ed,0xb67c393a,0x30b2b564,0xbbe23bf1,0xbbea3b88,0x31792fd6,
0xb3c62a48,0xb9cb3b25,0xbbc33bfe,0x3984b732,0xb8c436d7,0xb30337e3,0xba6d3b3b,0x3bcebaf6,0xb4a53913,0x3be2ba4f,0x3ba8ba2f,0x3179b8ec,
0x378bae46,0x3984bb99,0x3b0ebbf6,0xb9cb3505,0x3ba8ba2f,0xb303b444,0x34a5b913,0xbbce3bb6,0x3b0ebbf6,0xbb77393a,0xb78b2e46,0xb5c23a0f,
0x2a48b8c4,0xbbfa3a8a,0xbbfe3a6d,0x2cb5389b,0xbb3b381d,0xafd639cb,0xb6d73add,0x3bf1b984,0xb9ed3bea,0x3b99b848,0x395fb0b2,0x3505bac2,
0x356433c6,0x37e3bb77,0x3b88bbc3,0xbaf635c2,0x323e3872,0x3b99bac2,0x3bd9baa7,0xb505b848,0x3bd9baa7,0xb7e3b5c2,0xb23eb872,0xbaf63b77,
0xb23eb872,0xba0f3be2,0xbbd93aa7,0x393a3179,0xbbd93aa7,0x3a4fa648,0x323e3872,0x38ecbbff,0xb6d7b81d,0xbac23af6,0xbb3b3add,0x384837e3,
0xb95f3bea,0x3b50acb5,0x39ed30b2,0x367cbbfa,0x3b88b3c6,0xb179ba4f,0x3564bbc3,0xbbe238ec,0xaa48ba6d,0xb9cb3b99,0xbbfe38c4,0x39843505,
0x3913378b,0x3984bb25,0x3a2fbb0e,0xb9cbb732,0x2e46bba8,0xbbce37e3,0xbbf634a5,0x33033af6,0xba2f3b0e,0x3b772cb5,0x3913378b,0x35c2bbfa,
0x3bf6b4a5,0xb89bb8ec,0x2e46bba8,0xba8a3a4f,0xba6db6d7,0xb7e33b50,0xb8c43b3b,0x3af6367c,0x381d39ed,0x393aba8a,0x3addb95f,0xba0fb89b,
0xb0b2bb88,0xba4f3984,0xbbea3564,0x38ec39cb,0xb3c63bfe,0x3b25b848,0x3bc32a48,0xb732bac2,0x3b64361f,0x3444bb77,0x361fbb64,0xbbb6b5c2,
0xbb64b61f,0xacb53be2,0xb61f3b64,0x3bfa3179,0x3b64361f,0xafd6bbff,0x361fbb64,0xbbf12648,0xbb64b61f,0x35053bce,0xb61f3b64,0x3b99b303,
0xbbeab564,0xa6483b99,0xb0b23b88,0x3bff3505,0x3bc3aa48,0xb848bbb6,0xb3c6bbfe,0xbac23444,0xba6d36d7,0x3b50393a,0x38c43b3b,0x367cba0f,
0x381db9ed,0xbbe2afd6,0xbaddb95f,0x31793bf1,0x3bf634a5,0xb303bbb6,0xae46bba8,0xbbceb444,0xb913378b,0x3b773a0f,0x3a2f3b0e,0x35c2b93a,
0xae46bba8,0xba8a2fd6,0xbbf6b4a5,0x389b3bf1,0x3a2f3b0e,0xa648bb25,0x3913b78b,0xbbffb732,0xbb88b3c6,0x37323bce,0x35643bc3,0x3b253303,
0x2a48ba6d,0xbbb6b67c,0xbbfeb8c4,0x34443b50,0x3b3b3add,0xacb5ba8a,0x36d7b81d,0xbbfab89b,0xb9ed30b2,0x3bf139cb,0x395f3bea,0x2fd6b984,
0x3aa7323e,0xb93abbe2,0xb872bbd9,0xba0fb179,0x38723bd9,0x38eca648,0x3aa7323e,0xba4fbbff,0xbaa7b23e,0x3b253bce,0x38723bd9,0x3732b303,
0xb872bbd9,0xb444367c,0xbaa7b23e,0x3bb63b50,0xb95fb0b2,0x3a8a3bf1,0x39ed3bea,0x389b2fd6,0xbb88bbc3,0xa6483732,0xb56433c6,0x3bff3b25,
0xaa48b8c4,0xbac2b7e3,0xbbfeba6d,0x38483af6,0x3b3b381d,0xbb50bbfa,0xb6d7badd,0xb67c2cb5,0x378b2e46,0xbb77bbfa,0xbb0ebbf6,0xb5c2acb5,
0x3ba83a2f,0xb89bba4f,0xb4a5b913,0xba8ab8ec,0x3b0e3bf6,0xa648b505,0x378b2e46,0xbbffbb99,0x34a53913,0x38483444,0x3ba83a2f,0xbac2bbb6,
0xb3c6aa48,0x3bf13bff,0x3bc33bfe,0x2fd62648,0xb8c4b6d7,0x3b993bce,0x3a6d3b3b,0x35053303,0xbaddb9ed,0x3af63b50,0x381d395f,0x37e3367c,
0xbbeabb88,0x3a0f3a8a,0x30b23564,0x393a389b,0x3c003c00,0x2fd62648,0,0x3bf13bff,0x3c003c00,0x35053303,0,0x3b993bce,
0x3c003c00,0x37e3367c,0,0x3af63b50,0x3c003c00,0x393a389b,0,0x3a0f3a8a,0xbbc3bbfe,0xb5c2acb5,0x33c62a48,0xbb77bbfa,
0xba6dbb3b,0xba8ab8ec,0x38c436d7,0xb89bba4f,0xb81db95f,0xbbffbb99,0x3add39ed,0xa648b505,0xb0b2b564,0xbac2bbb6,0x3bea3b88,0x38483444,
0x3b0e3bf6,0x389b2fd6,0xb78bae46,0x3a8a3bf1,0x34a53913,0x3bff3b25,0xbba8ba2f,0xa6483732,0xb78bae46,0x38483af6,0xbb0ebbf6,0xbac2b7e3,
0xbba8ba2f,0xb67c2cb5,0xb4a5b913,0xbb50bbfa,0xb9edbbea,0xba0fb179,0x395f30b2,0xb93abbe2,0x3564b3c6,0xba4fbbff,0x3b883bc3,0x38eca648,
0x3bfe3a6d,0x3732b303,0x2a4838c4,0x3b253bce,0x36d73add,0x3bb63b50,0xbb3bb81d,0xb444367c,0x38723bd9,0x3b253303,0xbaa7b23e,0x37323bce,
0xbaa7b23e,0x34443b50,0xb872bbd9,0xbbb6b67c,0xb872bbd9,0xbbfab89b,0x3aa7323e,0xacb5ba8a,0x3aa7323e,0x2fd6b984,0x38723bd9,0x3bf139cb,
0xb564bbc3,0xbbceb444,0x3b8833c6,0xb303bbb6,0x3bfe38c4,0x35c2b93a,0xaa483a6d,0x3b773a0f,0xb6d7381d,0x389b3bf1,0xbb3bbadd,0xba8a2fd6,
0xb95fbbea,0xbbffb732,0x39edb0b2,0xa648bb25,0x2e463ba8,0x3bff3505,0xbbf6b4a5,0xa6483b99,0xba2fbb0e,0xbac23444,0x3913b78b,0xb848bbb6,
0x3bf634a5,0x367cba0f,0x2e463ba8,0x3b50393a,0xb913378b,0x31793bf1,0xba2fbb0e,0xbbe2afd6,0x30b2bb88,0xbbb6b5c2,0x3bea3564,0x3444bb77,
0x33c63bfe,0x3bfa3179,0xbbc32a48,0xacb53be2,0xb8c4bb3b,0xbbf12648,0x3a6db6d7,0xafd6bbff,0x3add395f,0x3b99b303,0xb81d39ed,0x35053bce,
0xb61f3b64,0x3af6367c,0xbb64b61f,0xb7e33b50,0x361fbb64,0xba0fb89b,0x3b64361f,0x393aba8a,0xb61f3b64,0x38ec39cb,0xbb64b61f,0xba4f3984,
0x361fbb64,0xb732bac2,0x3b64361f,0x3b25b848,0x38c4bb3b,0xb9cbb732,0x3a6d36d7,0x3984bb25,0xbadd395f,0x33033af6,0xb81db9ed,0xbbce37e3,
0x3beab564,0x35c2bbfa,0x30b23b88,0x3b772cb5,0xbbc3aa48,0xba8a3a4f,0x33c6bbfe,0xb89bb8ec,0xba2f3b0e,0x384837e3,0xb913b78b,0xbac23af6,
0x3bf6b4a5,0x367cbbfa,0xae463ba8,0x3b50acb5,0xb913b78b,0xbbe238ec,0x3a2fbb0e,0xb179ba4f,0xae463ba8,0x39843505,0xbbf634a5,0xb9cb3b99,
0x3b3bbadd,0xb505b848,0x36d7381d,0x3b99bac2,0xb9edb0b2,0xbaf63b77,0x395fbbea,0xb7e3b5c2,0xb5643bc3,0x393a3179,0xbb8833c6,0xba0f3be2,
0x3bfeb8c4,0x38ecbbff,0x2a483a6d,0x3a4fa648,0xbbd93aa7,0x2cb5389b,0xb23eb872,0xbbfa3a8a,0x323e3872,0x3bf1b984,0xbbd93aa7,0xafd639cb,
0x3bd9baa7,0x3505bac2,0x323e3872,0x3b99b848,0xb23eb872,0xbaf635c2,0x3bd9baa7,0x37e3bb77,0x3bfeba6d,0x3179b8ec,0xaa4838c4,0x3be2ba4f,
0x36d7badd,0xb9cb3505,0x3b3bb81d,0x3984bb99,0xb95f30b2,0xbbce3bb6,0x39edbbea,0xb303b444,0xbb883bc3,0xb5c23a0f,0xb564b3c6,0xbb77393a,
0xbba83a2f,0xb67c393a,0x34a5b913,0xbb503a0f,0xbb0e3bf6,0x31792fd6,0xb78b2e46,0xbbe23bf1,0xb4a53913,0x3984b732,0xbba83a2f,0xb9cb3b25,
0x378bae46,0x3bcebaf6,0xbb0e3bf6,0xb30337e3,0x3addb9ed,0x38ecb984,0xb81d395f,0x3a4fb9cb,0x3beabb88,0x3732b848,0xb0b23564,0x3b25bac2,
0x3bc3bbfe,0x3444b5c2,0x33c6aa48,0x3bb6bb77,0x3a6dbb3b,0x2cb5b179,0x38c4b6d7,0x3bfabbe2,0xb9a839a8,0xba4f39cb,0x39a8b9a8,0xb8ec3984,
0xb9a839a8,0xbb253ac2,0x39a8b9a8,0xb7323848,0xb9a839a8,0xbbb63b77,0x39a8b9a8,0xb44435c2,0xb9a839a8,0xbbfa3be2,0x39a8b9a8,0xacb53179,
0x381db95f,0x3b50ba0f,0xbadd39ed,0x367cb93a,0x30b2b564,0x3be2bbf1,0xbbea3b88,0xb179afd6,0xb3c62a48,0x39cbbb25,0xbbc33bfe,0xb9843732,
0xb8c436d7,0x3303b7e3,0xba6d3b3b,0xbbce3af6,0xb4a53913,0xbbe23a4f,0x3ba8ba2f,0xb17938ec,0x378bae46,0xb9843b99,0x3b0ebbf6,0x39cbb505,
0x3ba8ba2f,0x33033444,0x34a5b913,0x3bcebbb6,0x3b0ebbf6,0x3b77b93a,0xb78b2e46,0x35c2ba0f,0x2a48b8c4,0x3bfaba8a,0xbbfe3a6d,0xacb5b89b,
0xbb3b381d,0x2fd6b9cb,0xb6d73add,0xbbf13984,0xb9ed3bea,0xbb993848,0x395fb0b2,0xb5053ac2,0x356433c6,0xb7e33b77,0x3b88bbc3,0x3af6b5c2,
0x323e3872,0xbb993ac2,0x3bd9baa7,0x35053848,0x3bd9baa7,0x37e335c2,0xb23eb872,0x3af6bb77,0xb23eb872,0x3a0fbbe2,0xbbd93aa7,0xb93ab179,
0xbbd93aa7,0xba4f2648,0x323e3872,0xb8ec3bff,0xb6d7b81d,0x3ac2baf6,0xbb3b3add,0xb848b7e3,0xb95f3bea,0xbb502cb5,0x39ed30b2,0xb67c3bfa,
0x3b88b3c6,0x31793a4f,0x3564bbc3,0x3be2b8ec,0xaa48ba6d,0x39cbbb99,0xbbfe38c4,0xb984b505,0x3913378b,0xb9843b25,0x3a2fbb0e,0x39cb3732,
0x2e46bba8,0x3bceb7e3,0xbbf634a5,0xb303baf6,0xba2f3b0e,0xbb77acb5,0x3913378b,0xb5c23bfa,0x3bf6b4a5,0x389b38ec,0x2e46bba8,0x3a8aba4f,
0xba6db6d7,0x37e3bb50,0xb8c43b3b,0xbaf6b67c,0x381d39ed,0xb93a3a8a,0x3addb95f,0x3a0f389b,0xb0b2bb88,0x3a4fb984,0xbbea3564,0xb8ecb9cb,
0xb3c63bfe,0xbb253848,0x3bc32a48,0x37323ac2,0x3b64361f,0xb4443b77,0x361fbb64,0x3bb635c2,0xbb64b61f,0x2cb5bbe2,0xb61f3b64,0xbbfab179,
0x3b64361f,0x2fd63bff,0x361fbb64,0x3bf1a648,0xbb64b61f,0xb505bbce,0xb61f3b64,0xbb993303,0xbbeab564,0x2648bb99,0xb0b23b88,0xbbffb505,
0x3bc3aa48,0x38483bb6,0xb3c6bbfe,0x3ac2b444,0xba6d36d7,0xbb50b93a,0x38c43b3b,0xb67c3a0f,0x381db9ed,0x3be22fd6,0xbaddb95f,0xb179bbf1,
0x3bf634a5,0x33033bb6,0xae46bba8,0x3bce3444,0xb913378b,0xbb77ba0f,0x3a2f3b0e,0xb5c2393a,0xae46bba8,0x3a8aafd6,0xbbf6b4a5,0xb89bbbf1,
0x3a2f3b0e,0x26483b25,0x3913b78b,0x3bff3732,0xbb88b3c6,0xb732bbce,0x35643bc3,0xbb25b303,0x2a48ba6d,0x3bb6367c,0xbbfeb8c4,0xb444bb50,
0x3b3b3add,0x2cb53a8a,0x36d7b81d,0x3bfa389b,0xb9ed30b2,0xbbf1b9cb,0x395f3bea,0xafd63984,0x3aa7323e,0x393a3be2,0xb872bbd9,0x3a0f3179,
0x38723bd9,0xb8ec2648,0x3aa7323e,0x3a4f3bff,0xbaa7b23e,0xbb25bbce,0x38723bd9,0xb7323303,0xb872bbd9,0x3444b67c,0xbaa7b23e,0xbbb6bb50,
0xb95fb0b2,0xba8abbf1,0x39ed3bea,0xb89bafd6,0xbb88bbc3,0x2648b732,0xb56433c6,0xbbffbb25,0xaa48b8c4,0x3ac237e3,0xbbfeba6d,0xb848baf6,
0x3b3b381d,0x3b503bfa,0xb6d7badd,0x367cacb5,0x378b2e46,0x3b773bfa,0xbb0ebbf6,0x35c22cb5,0x3ba83a2f,0x389b3a4f,0xb4a5b913,0x3a8a38ec,
0x3b0e3bf6,0x26483505,0x378b2e46,0x3bff3b99,0x34a53913,0xb848b444,0x3ba83a2f,0x3ac23bb6,0xb3c6aa48,0xbbf1bbff,0x3bc33bfe,0xafd6a648,
0xb8c4b6d7,0xbb99bbce,0x3a6d3b3b,0xb505b303,0xbaddb9ed,0xbaf6bb50,0x381d395f,0xb7e3b67c,0xbbeabb88,0xba0fba8a,0x30b23564,0xb93ab89b,
0x3c003c00,0xba4fb9cb,0,0xb8ecb984,0x3c003c00,0xbb25bac2,0,0xb732b848,0x3c003c00,0xbbb6bb77,0,0xb444b5c2,
0x3c003c00,0xbbfabbe2,0,0xacb5b179,0x33c62a48,0x367c393a,0x3bc33bfe,0xbb50ba0f,0x38c436d7,0xb1792fd6,0x3a6d3b3b,0xbbe2bbf1,
0x3add39ed,0xb984b732,0x381d395f,0xb9cbbb25,0x3bea3b88,0xbbcebaf6,0x30b23564,0xb303b7e3,0xbb0ebbf6,0x3be23a4f,0x378b2e46,0x317938ec,
0xb4a5b913,0x39843b99,0x3ba83a2f,0xb9cbb505,0x378b2e46,0xb3033444,0x3b0e3bf6,0xbbcebbb6,0x3ba83a2f,0xbb77b93a,0x34a53913,0xb5c2ba0f,
0xb95fb0b2,0x2cb5b89b,0xb9edbbea,0x3bfa3a8a,0xbb88bbc3,0x3bf13984,0x3564b3c6,0x2fd639cb,0xaa48b8c4,0x35053ac2,0x3bfe3a6d,0xbb99b848,
0x3b3b381d,0xbaf6b5c2,0x36d73add,0xb7e3bb77,0x38723bd9,0xbb99bac2,0xbaa7b23e,0x3505b848,0xbaa7b23e,0x37e3b5c2,0xb872bbd9,0x3af63b77,
0xb872bbd9,0x3a0f3be2,0x3aa7323e,0xb93a3179,0x3aa7323e,0xba4fa648,0x38723bd9,0xb8ecbbff,0x3b8833c6,0xb84837e3,0x35643bc3,0xbac2baf6,
0xaa483a6d,0xb67cbbfa,0xbbfeb8c4,0x3b502cb5,0xbb3bbadd,0x3be238ec,0x36d7b81d,0xb1793a4f,0x39edb0b2,0xb9843505,0x395f3bea,0xb9cbbb99,
0xae46bba8,0x39843b25,0x3bf634a5,0xb9cb3732,0x3a2f3b0e,0xbbceb7e3,0xb913378b,0x3303baf6,0xbbf6b4a5,0x3b77acb5,0xae46bba8,0x35c23bfa,
0x3913b78b,0xb89b38ec,0x3a2f3b0e,0xba8aba4f,0xbbeab564,0x3af6b67c,0x30b2bb88,0x37e33b50,0x3bc3aa48,0xba0f389b,0x33c63bfe,0xb93aba8a,
0xba6d36d7,0x38ecb9cb,0xb8c4bb3b,0x3a4f3984,0x381db9ed,0xb7323ac2,0x3add395f,0xbb25b848,0xb61f3b64,0xb444bb77,0xbb64b61f,0x3bb6b5c2,
0x361fbb64,0x2cb53be2,0x3b64361f,0xbbfa3179,0xb61f3b64,0x2fd6bbff,0xbb64b61f,0x3bf12648,0x361fbb64,0xb5053bce,0x3b64361f,0xbb99b303,
0x3a6d36d7,0xbbff3505,0xb8c43b3b,0xa648bb99,0xb81db9ed,0x3ac23444,0x3addb95f,0xb8483bb6,0x30b23b88,0xb67cba0f,0xbbea3564,0x3b50b93a,
0x33c6bbfe,0xb1793bf1,0x3bc32a48,0xbbe22fd6,0x3a2fbb0e,0xb3033bb6,0x3913378b,0xbbce3444,0xbbf634a5,0x3b77ba0f,0x2e46bba8,0x35c2393a,
0x3913378b,0xba8aafd6,0xba2f3b0e,0x389bbbf1,0x2e46bba8,0xa6483b25,0x3bf6b4a5,0xbbff3732,0xb6d7b81d,0x3b25b303,0x3b3bbadd,0xb7323bce,
0xb95f3bea,0x3444bb50,0xb9edb0b2,0x3bb6b67c,0x3b88b3c6,0xbbfa389b,0xb5643bc3,0x2cb5ba8a,0xaa48ba6d,0x2fd63984,0x3bfeb8c4,0xbbf139cb,
0xbbd93aa7,0x393abbe2,0xb23eb872,0x3a0fb179,0x323e3872,0xb8eca648,0xbbd93aa7,0x3a4fbbff,0x3bd9baa7,0xbb253bce,0x323e3872,0xb732b303,
0xb23eb872,0x3444367c,0x3bd9baa7,0xbbb63b50,0xaa4838c4,0xb89b2fd6,0xbbfe3a6d,0x3a8abbf1,0x3b3bb81d,0xbbff3b25,0xb6d73add,0xa648b732,
0x39edbbea,0xb8483af6,0x395fb0b2,0xbac237e3,0xb564b3c6,0x367c2cb5,0x3b88bbc3,0xbb503bfa,0x3ba8ba2f,0xbb773bfa,0xb4a53913,0xb5c22cb5,
0x3b0ebbf6,0xb89b3a4f,0x378bae46,0xba8a38ec,0x34a5b913,0xa6483505,0x3ba8ba2f,0xbbff3b99,0xb78b2e46,0x3848b444,0x3b0ebbf6,0xbac23bb6,
0x381db95f,0x2fd6a648,0x3addb9ed,0xbbf13bff,0x30b2b564,0x3505b303,0x3beabb88,0xbb993bce,0xb3c62a48,0x37e3b67c,0x3bc3bbfe,0xbaf63b50,
0xb8c436d7,0x393ab89b,0x3a6dbb3b,0xba0f3a8a,0xb9a839a8,0x3bf1bbff,0x39a8b9a8,0xafd62648,0xb9a839a8,0x3b99bbce,0x39a8b9a8,0xb5053303,
0xb9a839a8,0x3af6bb50,0x39a8b9a8,0xb7e3367c,0xb9a839a8,0x3a0fba8a,0x39a8b9a8,0xb93a389b,0xbadd39ed,0x35c2acb5,0xb81d395f,0x3b77bbfa,
0xbbea3b88,0x3a8ab8ec,0xb0b23564,0x389bba4f,0xbbc33bfe,0x3bffbb99,0x33c6aa48,0x2648b505,0xba6d3b3b,0x3ac2bbb6,0x38c4b6d7,0xb8483444,
0x34a5b913,0xba8a3bf1,0xbba83a2f,0x389bafd6,0xb78b2e46,0x26483732,0xbb0e3bf6,0x3bffbb25,0xbba83a2f,0x3ac2b7e3,0xb4a53913,0x3848baf6,
0xbb0e3bf6,0x3b50bbfa,0x378bae46,0xb67cacb5,0x3bfeba6d,0xba0f3179,0x2a48b8c4,0xb93a3be2,0x36d7badd,0xba4f3bff,0xbb3b381d,0x38ec2648,
0xb95f30b2,0x37323303,0xb9ed3bea,0x3b25bbce,0xbb883bc3,0x3bb6bb50,0x356433c6,0xb444b67c,0x323e3872,0x3732bbce,0x3bd9baa7,0xbb253303,
0x3bd9baa7,0xbbb6367c,0xb23eb872,0xb4443b50,0xb23eb872,0xacb53a8a,0xbbd93aa7,0x3bfab89b,0xbbd93aa7,0x3bf1b9cb,0x323e3872,0xafd6b984,
0xbb3b3add,0x3bceb444,0x36d7381d,0x3303bbb6,0x39ed30b2,0xb5c2b93a,0x395fbbea,0xbb773a0f,0x3564bbc3,0xb89b3bf1,0xbb8833c6,0x3a8a2fd6,
0xbbfe38c4,0x3bffb732,0x2a483a6d,0x2648bb25,0xb913b78b,0x26483b99,0xba2f3b0e,0x3bffb505,0xae463ba8,0x3848bbb6,0x3bf6b4a5,0xbac2b444,
0x3a2fbb0e,0xbb50393a,0xb913b78b,0x367c3a0f,0xbbf634a5,0x3be2afd6,0xae463ba8,0x3179bbf1,0x38c4bb3b,0xbbb635c2,0xba6db6d7,0x34443b77,
0xbadd395f,0x3bfab179,0x381d39ed,0xacb5bbe2,0x3beab564,0xbbf1a648,0xb0b2bb88,0xafd63bff,0xbbc3aa48,0x3b993303,0xb3c63bfe,0x3505bbce,
0x3b64361f,0xb7e3bb50,0x361fbb64,0xbaf6367c,0xbb64b61f,0x393a3a8a,0xb61f3b64,0x3a0fb89b,0x3b64361f,0xba4fb984,0x361fbb64,0xb8ec39cb,
0xbb64b61f,0x3b253848,0xb61f3b64,0x3732bac2,0xb0b23b88,0x39cbb732,0x3bea3564,0xb984bb25,0xb3c6bbfe,0xb3033af6,0xbbc32a48,0x3bce37e3,
0x38c43b3b,0xb5c2bbfa,0x3a6db6d7,0xbb772cb5,0xbaddb95f,0x3a8a3a4f,0xb81d39ed,0x389bb8ec,0xbbf6b4a5,0x3ac23af6,0x2e463ba8,0x3848b7e3,
0x3913b78b,0xbb50acb5,0xba2fbb0e,0x367c3bfa,0x2e463ba8,0x3179ba4f,0x3bf634a5,0xbbe2b8ec,0xba2fbb0e,0x39cb3b99,0xb913378b,0x3984b505,
0xb564bbc3,0xb5053848,0xbb88b3c6,0x3b993ac2,0x3bfe38c4,0xbaf6bb77,0x2a48ba6d,0xb7e335c2,0xb6d7381d,0x393ab179,0x3b3b3add,0xba0fbbe2,
0xb95fbbea,0x38ec3bff,0xb9ed30b2,0x3a4f2648,0x3aa7323e,0xbbfaba8a,0xb872bbd9,0xacb5389b,0x38723bd9,0xafd6b9cb,0x3aa7323e,0xbbf1b984,
0xbaa7b23e,0x3b993848,0x38723bd9,0xb505bac2,0xb872bbd9,0x37e33b77,0xbaa7b23e,0x3af635c2,0x39ed3bea,0xb179b8ec,0x395f30b2,0xbbe2ba4f,
0xb56433c6,0x39cb3505,0x3b883bc3,0xb984bb99,0xbbfeba6d,0x3bce3bb6,0x2a4838c4,0x3303b444,0xb6d7badd,0x35c23a0f,0xbb3bb81d,0x3b77393a,
0xb78bae46,0x3b503a0f,0x3b0e3bf6,0xb67cb93a,0xbba8ba2f,0x3be23bf1,0x34a53913,0x3179afd6,0xbb0ebbf6,0x39cb3b25,0xb78bae46,0x39843732,
0xb4a5b913,0x330337e3,0xbba8ba2f,0x3bce3af6,0xbbc3bbfe,0x38ec3984,0xb3c6aa48,0x3a4f39cb,0xba6dbb3b,0x37323848,0xb8c4b6d7,0x3b253ac2,
0xb81db95f,0x344435c2,0xbaddb9ed,0x3bb63b77,0xb0b2b564,0x2cb53179,0xbbeabb88,0x3bfa3be2,0x3c003c00,0x3a4f39cb,0,0x38ec3984,
0x3c003c00,0x3b253ac2,0,0x37323848,0x3c003c00,0x3bb63b77,0,0x344435c2,0x3c003c00,0x3bfa3be2,0,0x2cb53179,
0x33c62a48,0xb67cb93a,0x3bc33bfe,0x3b503a0f,0x38c436d7,0x3179afd6,0x3a6d3b3b,0x3be23bf1,0x3add39ed,0x39843732,0x381d395f,0x39cb3b25,
0x3bea3b88,0x3bce3af6,0x30b23564,0x330337e3,0xbb0ebbf6,0xbbe2ba4f,0x378b2e46,0xb179b8ec,0xb4a5b913,0xb984bb99,0x3ba83a2f,0x39cb3505,
0x378b2e46,0x3303b444,0x3b0e3bf6,0x3bce3bb6,0x3ba83a2f,0x3b77393a,0x34a53913,0x35c23a0f,0xb95fb0b2,0xacb5389b,0xb9edbbea,0xbbfaba8a,
0xbb88bbc3,0xbbf1b984,0x3564b3c6,0xafd6b9cb,0xaa48b8c4,0xb505bac2,0x3bfe3a6d,0x3b993848,0x3b3b381d,0x3af635c2,0x36d73add,0x37e33b77,
0x38723bd9,0x3b993ac2,0xbaa7b23e,0xb5053848,0xbaa7b23e,0xb7e335c2,0xb872bbd9,0xbaf6bb77,0xb872bbd9,0xba0fbbe2,0x3aa7323e,0x393ab179,
0x3aa7323e,0x3a4f2648,0x38723bd9,0x38ec3bff,0x3b8833c6,0x3848b7e3,0x35643bc3,0x3ac23af6,0xaa483a6d,0x367c3bfa,0xbbfeb8c4,0xbb50acb5,
0xbb3bbadd,0xbbe2b8ec,0x36d7b81d,0x3179ba4f,0x39edb0b2,0x3984b505,0x395f3bea,0x39cb3b99,0xae46bba8,0xb984bb25,0x3bf634a5,0x39cbb732,
0x3a2f3b0e,0x3bce37e3,0xb913378b,0xb3033af6,0xbbf6b4a5,0xbb772cb5,0xae46bba8,0xb5c2bbfa,0x3913b78b,0x389bb8ec,0x3a2f3b0e,0x3a8a3a4f,
0xbbeab564,0xbaf6367c,0x30b2bb88,0xb7e3bb50,0x3bc3aa48,0x3a0fb89b,0x33c63bfe,0x393a3a8a,0xba6d36d7,0xb8ec39cb,0xb8c4bb3b,0xba4fb984,
0x381db9ed,0x3732bac2,0x3add395f,0x3b253848,0xb61f3b64,0x34443b77,0xbb64b61f,0xbbb635c2,0x361fbb64,0xacb5bbe2,0x3b64361f,0x3bfab179,
0xb61f3b64,0xafd63bff,0xbb64b61f,0xbbf1a648,0x361fbb64,0x3505bbce,0x3b64361f,0x3b993303,0x3a6d36d7,0x3bffb505,0xb8c43b3b,0x26483b99,
0xb81db9ed,0xbac2b444,0x3addb95f,0x3848bbb6,0x30b23b88,0x367c3a0f,0xbbea3564,0xbb50393a,0x33c6bbfe,0x3179bbf1,0x3bc32a48,0x3be2afd6,
0x3a2fbb0e,0x3303bbb6,0x3913378b,0x3bceb444,0xbbf634a5,0xbb773a0f,0x2e46bba8,0xb5c2b93a,0x3913378b,0x3a8a2fd6,0xba2f3b0e,0xb89b3bf1,
0x2e46bba8,0x2648bb25,0x3bf6b4a5,0x3bffb732,0xb6d7b81d,0xbb253303,0x3b3bbadd,0x3732bbce,0xb95f3bea,0xb4443b50,0xb9edb0b2,0xbbb6367c,
0x3b88b3c6,0x3bfab89b,0xb5643bc3,0xacb53a8a,0xaa48ba6d,0xafd6b984,0x3bfeb8c4,0x3bf1b9cb,0xbbd93aa7,0xb93a3be2,0xb23eb872,0xba0f3179,
0x323e3872,0x38ec2648,0xbbd93aa7,0xba4f3bff,0x3bd9baa7,0x3b25bbce,0x323e3872,0x37323303,0xb23eb872,0xb444b67c,0x3bd9baa7,0x3bb6bb50,
0xaa4838c4,0x389bafd6,0xbbfe3a6d,0xba8a3bf1,0x3b3bb81d,0x3bffbb25,0xb6d73add,0x26483732,0x39edbbea,0x3848baf6,0x395fb0b2,0x3ac2b7e3,
0xb564b3c6,0xb67cacb5,0x3b88bbc3,0x3b50bbfa,0x3ba8ba2f,0x3b77bbfa,0xb4a53913,0x35c2acb5,0x3b0ebbf6,0x389bba4f,0x378bae46,0x3a8ab8ec,
0x34a5b913,0x2648b505,0x3ba8ba2f,0x3bffbb99,0xb78b2e46,0xb8483444,0x3b0ebbf6,0x3ac2bbb6,0x381db95f,0xafd62648,0x3addb9ed,0x3bf1bbff,
0x30b2b564,0xb5053303,0x3beabb88,0x3b99bbce,0xb3c62a48,0xb7e3367c,0x3bc3bbfe,0x3af6bb50,0xb8c436d7,0xb93a389b,0x3a6dbb3b,0x3a0fba8a,
0xb9a839a8,0xbbf13bff,0x39a8b9a8,0x2fd6a648,0xb9a839a8,0xbb993bce,0x39a8b9a8,0x3505b303,0xb9a839a8,0xbaf63b50,0x39a8b9a8,0x37e3b67c,
0xb9a839a8,0xba0f3a8a,0x39a8b9a8,0x393ab89b,0xbadd39ed,0xb5c22cb5,0xb81d395f,0xbb773bfa,0xbbea3b88,0xba8a38ec,0xb0b23564,0xb89b3a4f,
0xbbc33bfe,0xbbff3b99,0x33c6aa48,0xa6483505,0xba6d3b3b,0xbac23bb6,0x38c4b6d7,0x3848b444,0x34a5b913,0x3a8abbf1,0xbba83a2f,0xb89b2fd6,
0xb78b2e46,0xa648b732,0xbb0e3bf6,0xbbff3b25,0xbba83a2f,0xbac237e3,0xb4a53913,0xb8483af6,0xbb0e3bf6,0xbb503bfa,0x378bae46,0x367c2cb5,
0x3bfeba6d,0x3a0fb179,0x2a48b8c4,0x393abbe2,0x36d7badd,0x3a4fbbff,0xbb3b381d,0xb8eca648,0xb95f30b2,0xb732b303,0xb9ed3bea,0xbb253bce,
0xbb883bc3,0xbbb63b50,0x356433c6,0x3444367c,0x323e3872,0xb7323bce,0x3bd9baa7,0x3b25b303,0x3bd9baa7,0x3bb6b67c,0xb23eb872,0x3444bb50,
0xb23eb872,0x2cb5ba8a,0xbbd93aa7,0xbbfa389b,0xbbd93aa7,0xbbf139cb,0x323e3872,0x2fd63984,0xbb3b3add,0xbbce3444,0x36d7381d,0xb3033bb6,
0x39ed30b2,0x35c2393a,0x395fbbea,0x3b77ba0f,0x3564bbc3,0x389bbbf1,0xbb8833c6,0xba8aafd6,0xbbfe38c4,0xbbff3732,0x2a483a6d,0xa6483b25,
0xb913b78b,0xa648bb99,0xba2f3b0e,0xbbff3505,0xae463ba8,0xb8483bb6,0x3bf6b4a5,0x3ac23444,0x3a2fbb0e,0x3b50b93a,0xb913b78b,0xb67cba0f,
0xbbf634a5,0xbbe22fd6,0xae463ba8,0xb1793bf1,0x38c4bb3b,0x3bb6b5c2,0xba6db6d7,0xb444bb77,0xbadd395f,0xbbfa3179,0x381d39ed,0x2cb53be2,
0x3beab564,0x3bf12648,0xb0b2bb88,0x2fd6bbff,0xbbc3aa48,0xbb99b303,0xb3c63bfe,0xb5053bce,0x3b64361f,0x37e33b50,0x361fbb64,0x3af6b67c,
0xbb64b61f,0xb93aba8a,0xb61f3b64,0xba0f389b,0x3b64361f,0x3a4f3984,0x361fbb64,0x38ecb9cb,0xbb64b61f,0xbb25b848,0xb61f3b64,0xb7323ac2,
0xb0b23b88,0xb9cb3732,0x3bea3564,0x39843b25,0xb3c6bbfe,0x3303baf6,0xbbc32a48,0xbbceb7e3,0x38c43b3b,0x35c23bfa,0x3a6db6d7,0x3b77acb5,
0xbaddb95f,0xba8aba4f,0xb81d39ed,0xb89b38ec,0xbbf6b4a5,0xbac2baf6,0x2e463ba8,0xb84837e3,0x3913b78b,0x3b502cb5,0xba2fbb0e,0xb67cbbfa,
0x2e463ba8,0xb1793a4f,0x3bf634a5,0x3be238ec,0xba2fbb0e,0xb9cbbb99,0xb913378b,0xb9843505,0xb564bbc3,0x3505b848,0xbb88b3c6,0xbb99bac2,
0x3bfe38c4,0x3af63b77,0x2a48ba6d,0x37e3b5c2,0xb6d7381d,0xb93a3179,0x3b3b3add,0x3a0f3be2,0xb95fbbea,0xb8ecbbff,0xb9ed30b2,0xba4fa648,
0x3aa7323e,0x3bfa3a8a,0xb872bbd9,0x2cb5b89b,0x38723bd9,0x2fd639cb,0x3aa7323e,0x3bf13984,0xbaa7b23e,0xbb99b848,0x38723bd9,0x35053ac2,
0xb872bbd9,0xb7e3bb77,0xbaa7b23e,0xbaf6b5c2,0x39ed3bea,0x317938ec,0x395f30b2,0x3be23a4f,0xb56433c6,0xb9cbb505,0x3b883bc3,0x39843b99,
0xbbfeba6d,0xbbcebbb6,0x2a4838c4,0xb3033444,0xb6d7badd,0xb5c2ba0f,0xbb3bb81d,0xbb77b93a,0xb78bae46,0xbb50ba0f,0x3b0e3bf6,0x367c393a,
0xbba8ba2f,0xbbe2bbf1,0x34a53913,0xb1792fd6,0xbb0ebbf6,0xb9cbbb25,0xb78bae46,0xb984b732,0xb4a5b913,0xb303b7e3,0xbba8ba2f,0xbbcebaf6,
0xbbc3bbfe,0xb8ecb984,0xb3c6aa48,0xba4fb9cb,0xba6dbb3b,0xb732b848,0xb8c4b6d7,0xbb25bac2,0xb81db95f,0xb444b5c2,0xbaddb9ed,0xbbb6bb77,
0xb0b2b564,0xacb5b179,0xbbeabb88,0xbbfabbe2,0x3c003c00,0x96480000,0x3c003c00,0xa311a248,0x3c003c00,0x9cb69a48,0x3c003c00,0xa452a3db,
0x3c003c00,0x9fdb9e48,0x3c003c00,0xa51ba4b6,0x3c003c00,0xa17fa0b6,0x3bff3c00,0xa5e4a57f,0x3c003c00,0x9fdb0000,0x3bfb3bfc,0xac6aabd9,
0x3bff3c00,0xa5e4a3db,0x3bf93bfa,0xad65ace7,0x3bfe3bff,0xa8e8a7da,0x3bf63bf7,0xae5fade2,0x3bfd3bfe,0xaadea9e3,0x3bf23bf4,0xaf59aedc,
0x3c003c00,0xa3110000,0x3bf03bf4,0xafefaf0e,0x3bfe3bff,0xa94da711,0x3be83bed,0xb0d7b067,0x3bfb3bfd,0xac6aab11,0x3bdf3be4,0xb1b6b147,
0x3bf63bf9,0xae2dad4c,0x3bd43bda,0xb294b226,0x3c003c00,0xa51b0000,0x3bdf3be6,0xb1b6b115,0x3bfc3bfe,0xaba7a91b,0x3bcf3bd7,0xb2f7b257,
0x3bf63bf9,0xae5fad1a,0x3bbc3bc6,0xb41ab396,0x3bec3bf1,0xb074afa4,0x3ba53bb1,0xb4b7b469,0x3bff3c00,0xa6ad0000,0x3bc83bd4,0xb371b2a1,
0x3bfa3bfd,0xad00aaac,0x3bac3bbb,0xb487b420,0x3bef3bf5,0xb029aeaa,0x3b8b3b9d,0xb552b4ed,0x3bde3be7,0xb1cfb0fd,0x3b653b79,0xb61ab5b6,
0x3bff3c00,0xa81f0000,0x3bab3bbc,0xb493b414,0x3bf63bfc,0xae2dac1f,0x3b813b97,0xb58db511,0x3be53bef,0xb122b01d,0x3b4f3b69,0xb682b608,
0x3bcc3bda,0xb328b226,0x3b163b33,0xb76fb6f9,0x3bfe3c00,0xa8e80000,0x3b873ba0,0xb56ab4d5,0x3bf23bfa,0xaf59ace7,0x3b4c3b6b,0xb68db5fd,
0x3bda3be8,0xb219b0e4,0x3b073b2b,0xb7a6b71b,0x3bb73bca,0xb43eb34c,0x3ab63ae0,0xb85ab817,0x3bfe3c00,0xa9b10000,0x3b5e3b80,0xb63cb593,
0x3bee3bf8,0xb042adb0,0x3b103b39,0xb785b6e3,0x3bce3be0,0xb30fb1aa,0x3ab33ae3,0xb85fb812,0x3b9e3bb7,0xb4e7b438,0x3a493a7f,0xb8f3b8ab,
0x3bfd3c00,0xaa7a0000,0x3b2f3b5a,0xb70ab64e,0x3be83bf6,0xb0d7ae78,0x3acb3aff,0xb83ab7c2,0x3bbf3bd6,0xb402b26f,0x3a543a92,0xb8e5b891,
0x3b813ba2,0xb58db4c9,0x39cd3a13,0xb982b935,0x3bfd3c00,0xab430000,0x3afb3b30,0xb7d2b705,0x3be23bf3,0xb16caf40,0x3a7e3abf,0xb8adb84d,
0x3bae3bcb,0xb47bb334,0x39eb3a37,0xb962b909,0x3b603b8a,0xb631b558,0x3946399b,0xba04b9b5,0x3bfc3c00,0xac060000,0x3ac13b02,0xb84ab7b7,
0x3bdc3bf0,0xb201b004,0x3a293a78,0xb91bb8b5,0x3b9c3bc0,0xb4f3b3f7,0x397939d4,0xb9d6b97b,0x3b3d3b70,0xb6d2b5e5,0x38b23918,0xba7aba2b,
0x3bfb3c00,0xac6a0000,0x3a813ad0,0xb8a8b832,0x3bd43bed,0xb294b067,0x39cd3a2b,0xb982b918,0x3b873bb2,0xb56ab45d,0x38fd3969,0xba41b9e5,
0x3b163b53,0xb76fb670,0x3815388c,0xbae1ba95,0x3bfa3c00,0xacce0000,0x3a3d3a99,0xb902b887,0x3bcc3be9,0xb328b0cb,0x396b39d8,0xb9e3b976,
0x3b713ba4,0xb5dfb4bd,0x387a38f6,0xbaa2ba47,0x3aeb3b33,0xb805b6f9,0x36dd37ee,0xbb3abaf3,0x3bf93c00,0xad330000,0x39f43a5e,0xb958b8d8,
0x3bc33be5,0xb3bab12e,0x39023980,0xba3db9d0,0x3b593b95,0xb654b51d,0x37dd387c,0xbaf7baa0,0x3abd3b11,0xb850b780,0x358136b5,0xbb83bb43,
0x3bf83c00,0xad970000,0x39a63a1f,0xb9aab927,0x3bba3be1,0xb426b191,0x38943922,0xba90ba23,0x3b3f3b84,0xb6c6b57c,0x36bb37f9,0xbb42baf0,
0x3a8c3aed,0xb899b802,0x341a3570,0xbbbcbb86,0x3bf73c00,0xadfb0000,0x395439dc,0xb9f8b972,0x3bb03bdc,0xb46fb1f4,0x382038bf,0xbadbba71,
0x3b243b72,0xb737b5da,0x358d36ee,0xbb81bb36,0x3a583ac6,0xb8e0b842,0x31533420,0xbbe3bbbb,0x3bf63c00,0xae5f0000,0x38fd3996,0xba41b9ba,
0x3ba53bd7,0xb4b7b257,0x374e3858,0xbb1ebab8,0x3b073b5f,0xb7a6b637,0x345735da,0xbbb3bb72,0x3a213a9c,0xb924b881,0x2cce3191,0xbbfabbe1,
0x3bf53c00,0xaec30000,0x38a3394d,0xba85b9fe,0x3b9a3bd2,0xb4ffb2b9,0x365437d8,0xbb59baf9,0x3ae83b4b,0xb80ab693,0x323234bd,0xbbd9bba4,
0x39e73a71,0xb966b8bf,0xa4522db0,0xbc00bbf8,0x3bf33c00,0xaf270000,0x38453900,0xbac4ba3f,0x3b8e3bcd,0xb546b31b,0x355236f9,0xbb8bbb33,
0x3ac73b36,0xb840b6ee,0x2f593334,0xbbf2bbcb,0x39aa3a43,0xb9a6b8fb,0xaef51a48,0xbbf4bc00,0x3bf23c00,0xaf8b0000,0x37c838b0,0xbafeba7c,
0x3b813bc7,0xb58db37d,0x344b3614,0xbbb5bb67,0x3aa53b20,0xb874b748,0x288430e4,0xbbffbbe8,0x396b3a13,0xb9e3b935,0xb263ad4c,0xbbd7bbf9,
0x3bf03c00,0xafef0000,0x36ff385d,0xbb32bab5,0x3b733bc1,0xb5d4b3df,0x327c3529,0xbbd6bb93,0x3a813b08,0xb8a8b7a1,0xa9b12d1a,0xbbfebbf9,
0x392939e1,0xba1db96d,0xb49fb160,0xbba9bbe3,0x3bef3c00,0xb0290000,0x36313807,0xbb60bae9,0x3b653bbb,0xb61ab420,0x305b3438,0xbbedbbb7,
0x3a5c3af0,0xb8dbb7f9,0xafef1e48,0xbbf0bc00,0x38e539ad,0xba54b9a4,0xb602b408,0xbb6abbbe,0x3bed3c00,0xb05b0000,0x355e375e,0xbb89bb1a,
0x3b573bb4,0xb65fb451,0x2c6a3288,0xbbfbbbd5,0x3a353ad6,0xb90cb828,0xb27cac51,0xbbd6bbfb,0x389e3976,0xba89b9d8,0xb759b558,0xbb1bbb8a,
0x3beb3c00,0xb08d0000,0x348736aa,0xbbacbb46,0x3b473bad,0xb6a4b481,0x16483099,0xbc00bbeb,0x3a0d3abc,0xb93cb852,0xb47bb080,0xbbaebbec,
0x3855393e,0xbababa0b,0xb850b69e,0xbabdbb49,0x3be93c00,0xb0be0000,0x335935f1,0xbbc9bb6e,0x3b373ba6,0xb6e8b4b1,0xac382d4c,0xbbfcbbf9,
0x39e33aa0,0xb96bb87c,0xb5b1b2d2,0xbb7abbd1,0x380a3905,0xbae8ba3b,0xb8eab7d8,0xba50baf9,0x3be73c00,0xb0f00000,0x319e3534,0xbbe0bb91,
0x3b273b9e,0xb72cb4e1,0xb042257f,0xbbeebc00,0x39b83a83,0xb999b8a6,0xb6ddb48d,0xbb3abbab,0x377a38c9,0xbb13ba69,0xb979b881,0xb9d6ba9c,
0x3be53c00,0xb1220000,0x2fbd3475,0xbbf1bbaf,0x3b163b97,0xb76fb511,0xb263a91b,0xbbd7bbfe,0x398b3a65,0xb9c5b8ce,0xb7feb5ab,0xbaeebb7b,
0x36dd388c,0xbb3aba95,0xb9fcb90e,0xb94fba33,0x3be33c00,0xb1530000,0x2c383365,0xbbfcbbc9,0x3b043b8f,0xb7b2b540,0xb43eae78,0xbbb7bbf6,
0x395d3a47,0xb9f0b8f6,0xb889b6c1,0xba97bb41,0x363c384d,0xbb5ebabf,0xba73b992,0xb8bcb9be,0x3be13c00,0xb1850000,0x217f31db,0xbc00bbdd,
0x3af13b86,0xb7f3b570,0xb546b12e,0xbb8ebbe5,0x392e3a27,0xba19b91d,0xb90cb7cd,0xba35bafc,0x3599380d,0xbb7fbae6,0xbadbba0b,0xb820b93e,
0x3bdf3c00,0xb1b60000,0xa9b1304e,0xbbfebbed,0x3ade3b7d,0xb81ab59f,0xb648b31b,0xbb5cbbcd,0x38fd3a07,0xba41b943,0xb986b867,0xb9c9baae,
0x34f33796,0xbb9cbb0b,0xbb35ba78,0xb6f4b8b5,0x3bdd3c00,0xb1e80000,0xae5f2d7e,0xbbf6bbf8,0x3acb3b74,0xb83ab5ce,0xb742b481,0xbb21bbad,
0x38cc39e5,0xba67b969,0xb9f8b8e2,0xb954ba56,0x344b3710,0xbbb5bb2e,0xbb7fbad9,0xb599b822,0x3bda3c00,0xb2190000,0xb0f028b6,0xbbe7bbff,
0x3ab63b6b,0xb85ab5fd,0xb81ab570,0xbadebb86,0x389939c3,0xba8cb98d,0xba60b956,0xb8d6b9f6,0x33403687,0xbbcbbb4e,0xbbb8bb2e,0xb432b710,
0x3bff3bff,0xa6ada648,0x3bfe3bff,0xa8e8a8b6,0x3bff3bff,0xa776a711,0x3bfe3bfe,0xa94da91b,0x3bff3bff,0xa81fa7da,0x3bfe3bfe,0xa9b1a97f,
0x3bff3bff,0xa884a852,0x3bfe3bfe,0xaa16a9e3,0x3bef3bf1,0xb029afd6,0x3bda3bdd,0xb219b1db,0x3bea3bed,0xb0a6b067,0x3bd43bd7,0xb294b257,
0x3be53be8,0xb122b0e4,0x3bce3bd1,0xb30fb2d2,0x3be03be3,0xb19eb160,0x3bc63bca,0xb389b34c,0x3bc83bce,0xb371b303,0x3b873b91,0xb56ab534,
0x3bba3bc1,0xb426b3df,0x3b733b7d,0xb5d4b59f,0x3bab3bb2,0xb493b45d,0x3b5e3b69,0xb63cb608,0x3b9a3ba2,0xb4ffb4c9,0x3b473b53,0xb6a4b670,
0x3b8b3b99,0xb552b505,0x3b073b1a,0xb7a6b75e,0x3b6f3b7d,0xb5ebb59f,0x3ade3af3,0xb81ab7ee,0x3b4f3b5f,0xb682b637,0x3ab33ac9,0xb85fb83d,
0x3b2c3b3e,0xb715b6cc,0x3a853a9c,0xb8a3b881,0x3b3a3b50,0xb6ddb67c,0x3a5c3a7c,0xb8dbb8b0,0x3b0a3b22,0xb79bb73d,0x3a193a3b,0xb92eb905,
0x3ad53af0,0xb82ab7f9,0x39d239f6,0xb97db956,0x3a9b3ab8,0xb884b858,0x398639ad,0xb9c9b9a4,0x3ad53af6,0xb82ab7e3,0x398b39ba,0xb9c5b996,
0x3a8c3ab1,0xb899b862,0x3929395b,0xba1db9f2,0x3a3d3a65,0xb902b8ce,0x38c138f6,0xba6fba47,0x39e73a13,0xb966b935,0x3855388c,0xbababa95,
0x3a5c3a8a,0xb8dbb89b,0x389938d8,0xba8cba5e,0x39f83a2b,0xb954b918,0x38153858,0xbae1bab8,0x398b39c3,0xb9c5b98d,0x371537a1,0xbb2cbb08,
0x39163951,0xba2db9fa,0x35f73687,0xbb6cbb4e,0x39d23a0f,0xb97db93a,0x371537b7,0xbb2cbb02,0x394f3992,0xb9fcb9be,0x35c83670,0xbb76bb53,
0x38c13909,0xba6fba37,0x346f351d,0xbbb0bb95,0x382a3877,0xbad5baa3,0x3219337d,0xbbdabbc7,0x39373984,0xba11b9cb,0x34cf3593,0xbba1bb80,
0x389438e7,0xba90ba52,0x327c3408,0xbbd6bbbe,0x37c8383d,0xbafebac9,0x2e9130e4,0xbbf5bbe8,0x36543710,0xbb59bb2e,0x16482aac,0xbc00bbfd,
0x388e38ec,0xba93ba4f,0x30d732a1,0xbbe8bbd4,0x3790382d,0xbb0dbad3,0x28e82e14,0xbbfebbf7,0x35eb36c1,0xbb6fbb41,0xaccea4b6,0xbbfabc00,
0x34323511,0xbbb8bb97,0xb201b036,0xbbdcbbee,0x37b23848,0xbb04bac2,0x96482bd9,0xbc00bbfc,0x35df36cc,0xbb71bb3e,0xb010ac1f,0xbbefbbfc,
0x33eb34ed,0xbbc0bb9d,0xb402b20d,0xbbbfbbdb,0x2fef31f4,0xbbf0bbdc,0xb5ebb4f9,0xbb6fbb9b,0x36313732,0xbb60bb25,0xb0f0ad7e,0xbbe7bbf8,
0x341a3529,0xbbbcbb93,0xb49fb31b,0xbba9bbcd,0x2fbd320d,0xbbf1bbdb,0xb6afb5ab,0xbb45bb7b,0xa4522aac,0xbc00bbfd,0xb850b7ac,0xbabdbb05,
0x349f35c2,0xbba9bb77,0xb4dbb365,0xbb9fbbc9,0x308d32ea,0xbbebbbd0,0xb715b5fd,0xbb2cbb6b,0x9fdb2c51,0xbc00bbfb,0xb894b812,0xba90bae3,
0xb109ad4c,0xbbe6bbf9,0xb982b90e,0xb9cdba33,0x32013444,0xbbdcbbb6,0xb721b5f1,0xbb2abb6e,0x26ad2edc,0xbbffbbf4,0xb8adb822,0xba7ebad9,
0xb05bab11,0xbbedbbfd,0xb9aab930,0xb9a6ba17,0xb4b7b2ea,0xbba5bbd0,0xba81ba1b,0xb8a8b92b,0x2d653179,0xbbf9bbe2,0xb89eb807,0xba89bae9,
0xadc99a48,0xbbf8bc00,0xb9afb92b,0xb9a1ba1b,0xb432b1aa,0xbbb8bbe0,0xba93ba27,0xb88eb91d,0xb6d2b587,0xbb3dbb82,0xbb45baf3,0xb6afb7ee,
0xa51b2cb5,0xbc00bbfa,0xb990b900,0xb9c0ba3f,0xb294af40,0xbbd4bbf3,0xba89ba13,0xb89eb935,0xb625b4bd,0xbb63bba4,0xbb47baf0,0xb6a4b7f9,
0xb865b780,0xbab0bb11,0xbbc5bb8f,0xb3a2b540,0xafefa648,0xbbf0bbff,0xba60b9dc,0xb8d6b972,0xb517b31b,0xbb96bbcd,0xbb35bad3,0xb6f4b82d,
0xb7feb693,0xbaeebb4b,0xbbc0bb84,0xb3ebb57c,0xb94ab8ab,0xba00ba7f,0xbbfdbbe9,0xaa7ab0cb,0xb340afd6,0xbbcbbbf1,0xbb0aba99,0xb79bb887,
0xb6d2b540,0xbb3dbb8f,0xbbaebb67,0xb47bb614,0xb8dbb828,0xba5cbad6,0xbbfbbbe0,0xac9cb1aa,0xba15b980,0xb933b9d0,0xbbecbbff,0x30742852,
0xb53ab303,0xbb90bbce,0xbb89bb30,0xb55eb705,0xb83ab6e3,0xbacbbb39,0xbbf2bbca,0xaf8bb34c,0xb9a1b8f6,0xb9afba47,0xbbf5bc00,0x2ec39e48,
0xbac1ba3b,0xb84ab905,0xbb92bbd0,0x352f32ea,0xb6c6b505,0xbb3fbb99,0xbbdcbba0,0xb201b4d5,0xb8fdb838,0xba41bacc,0xbbfebbfb,0x2a16ac83,
0xba50b9b1,0xb8eab99f,0xbbaebbe4,0x347b3147,0xbb4abad9,0xb699b822,0xbaf1bb5d,0x37f33642,0xb820b67c,0xbadbbb50,0xbbffbbe6,0xa884b115,
0xb9afb8f1,0xb9a1ba4b,0xbbd2bbf8,0x32c62db0,0xbae5ba56,0xb80fb8e2,0xbb2abb8c,0x3721354c,0xbbaebb58,0xb47bb659,0xba11baaa,0x3937386d,
0xb8d1b7e3,0xba64baf6,0xbbf2bc00,0x2f8ba248,0xba4db99b,0xb8eeb9b5,0xbb6fbbc1,0x35eb33df,0xbb5cbae3,0xb648b812,0xba6bbafc,0x38c737cd,
0xbbebbbb4,0xb08db451,0xb8f8b9be,0x3a453992,0xb974b89b,0xb9daba8a,0xbbb5bbed,0x344b304e,0xbad5ba33,0xb82ab90e,0xbad8bb58,0x38253659,
0xbbb3bb55,0xb457b665,0xb979ba37,0x39d63909,0xbc00bbed,0x9648b067,0xb764b8a0,0x3b183a87,0xba09b93a,0xb941ba0f,0xbb4abbaf,0x36993475,
0xbb45bab8,0xb6afb858,0xba11babf,0x3937384d,0xbbeabbab,0xb0a6b48d,0xb85ab943,0x3ab63a07,0xbbecbc00,0x30749a48,0xb493b6b5,0x3bab3b43,
0xba8cb9cb,0xb899b984,0xbab3bb46,0x385f36aa,0xbb9cbb28,0xb4f3b726,0xb91fb9fa,0x3a253951,0xbc00bbe4,0xa452b147,0xb631b828,0x3b603ad6,
0xbbb0bbee,0x346f3036,0xae5fb3df,0x3bf63bc1,0xbafeba4f,0xb7c8b8ec,0xb9f4bab5,0x3958385d,0xbbd8bb82,0xb24bb587,0xb80ab90e,0x3ae83a33,
0xbbf3bbfe,0x2f27a97f,0xb2f7b5da,0x3bcf3b72,0xbb4cbbb7,0x368d3438,0x2dc9ac1f,0x3bf83bfc,0xbb5cbac2,0xb648b848,0xb911b9fe,0x3a31394d,
0xbbf9bbc4,0xad33b3ae,0xb5b1b802,0x3b7a3aed,0xbbc5bbf9,0x33a22d1a,0xa94db26f,0x3bfe3bd6,0xbac4bb5d,0x38453642,0x346f2fa4,0x3bb03bf1,
0xbba5bb25,0xb4b7b732,0xb80fb927,0x3ae53a1f,0xbbffbbee,0x2884b036,0xb24bb5b6,0x3bd83b79,0xbb76bbd6,0x35c8326f,0x305ba7da,0x3bed3bff,
0xba19bae0,0x392e3817,0x374234c9,0x3b213ba2,0xbbd9bb77,0xb232b5c2,0xb5ebb832,0x3b6f3ad0,0xbbe8bc00,0x30d7a57f,0xa81fb288,0x3bff3bd5,
0xbb07bb95,0x37a6351d,0x34f33080,0x3b9c3bec,0xb94fba43,0x39fc38fb,0x38ea3780,0x3a503b11,0xbbf8bbb6,0xadc9b444,0xb328b64e,0x3bcc3b5a,
0xbbb7bbf8,0x343e2db0,0x3042a9e3,0x3bee3bfe,0xba7abb36,0x38b236ee,0x379034ed,0x3b0d3b9d,0xb86ab989,0x3aac39c7,0x3a0438fb,0x39463a43,
0xbc00bbe2,0x2311b179,0xac9cb414,0x3bfb3bbc,0xbb6abbd7,0x36023257,0x34b72f40,0x3ba53bf3,0xb9d2babc,0x397d3852,0x38f83775,0x3a453b14,
0xb6ddb8b5,0x3b3a3a78,0x3ae83a0b,0x380a393e,0xbbf2bbfa,0x2f8bacb5,0x2d33af0e,0x3bf93bf4,0xbb04bb9e,0x37b234e1,0x372c3451,0x3b273bb4,
0xb911ba27,0x3a31391d,0x3a0038e2,0x394a3a56,0xb4c3b796,0x3ba33b0b,0x3b8b3ae6,0x3552380d,0x4c004c00,0x26480000,0x4c004c00,0x33113248,
0x4c004c00,0x2cb62a48,0x4c004c00,0x345233db,0x4c004c00,0x2fdb2e48,0x4c004c00,0x351b34b6,0x4c004c00,0x317f30b6,0x4bff4c00,0x35e4357f,
0x4c004c00,0x2fdb0000,0x4bfb4bfc,0x3c6a3bd9,0x4bff4c00,0x35e433db,0x4bf94bfa,0x3d653ce7,0x4bfe4bff,0x38e837da,0x4bf64bf7,0x3e5f3de2,
0x4bfd4bfe,0x3ade39e3,0x4bf24bf4,0x3f593edc,0x4c004c00,0x33110000,0x4bf04bf4,0x3fef3f0e,0x4bfe4bff,0x394d3711,0x4be84bed,0x40d74067,
0x4bfb4bfd,0x3c6a3b11,0x4bdf4be4,0x41b64147,0x4bf64bf9,0x3e2d3d4c,0x4bd44bda,0x42944226,0x4c004c00,0x351b0000,0x4bdf4be6,0x41b64115,
0x4bfc4bfe,0x3ba7391b,0x4bcf4bd7,0x42f74257,0x4bf64bf9,0x3e5f3d1a,0x4bbc4bc6,0x441a4396,0x4bec4bf1,0x40743fa4,0x4ba54bb1,0x44b74469,
0x4bff4c00,0x36ad0000,0x4bc84bd4,0x437142a1,0x4bfa4bfd,0x3d003aac,0x4bac4bbb,0x44874420,0x4bef4bf5,0x40293eaa,0x4b8b4b9d,0x455244ed,
0x4bde4be7,0x41cf40fd,0x4b654b79,0x461a45b6,0x4bff4c00,0x381f0000,0x4bab4bbc,0x44934414,0x4bf64bfc,0x3e2d3c1f,0x4b814b97,0x458d4511,
0x4be54bef,0x4122401d,0x4b4f4b69,0x46824608,0x4bcc4bda,0x43284226,0x4b164b33,0x476f46f9,0x4bfe4c00,0x38e80000,0x4b874ba0,0x456a44d5,
0x4bf24bfa,0x3f593ce7,0x4b4c4b6b,0x468d45fd,0x4bda4be8,0x421940e4,0x4b074b2b,0x47a6471b,0x4bb74bca,0x443e434c,0x4ab64ae0,0x485a4817,
0x4bfe4c00,0x39b10000,0x4b5e4b80,0x463c4593,0x4bee4bf8,0x40423db0,0x4b104b39,0x478546e3,0x4bce4be0,0x430f41aa,0x4ab34ae3,0x485f4812,
0x4b9e4bb7,0x44e74438,0x4a494a7f,0x48f348ab,0x4bfd4c00,0x3a7a0000,0x4b2f4b5a,0x470a464e,0x4be84bf6,0x40d73e78,0x4acb4aff,0x483a47c2,
0x4bbf4bd6,0x4402426f,0x4a544a92,0x48e54891,0x4b814ba2,0x458d44c9,0x49cd4a13,0x49824935,0x4bfd4c00,0x3b430000,0x4afb4b30,0x47d24705,
0x4be24bf3,0x416c3f40,0x4a7e4abf,0x48ad484d,0x4bae4bcb,0x447b4334,0x49eb4a37,0x49624909,0x4b604b8a,0x46314558,0x4946499b,0x4a0449b5,
0x4bfc4c00,0x3c060000,0x4ac14b02,0x484a47b7,0x4bdc4bf0,0x42014004,0x4a294a78,0x491b48b5,0x4b9c4bc0,0x44f343f7,0x497949d4,0x49d6497b,
0x4b3d4b70,0x46d245e5,0x48b24918,0x4a7a4a2b,0x4bfb4c00,0x3c6a0000,0x4a814ad0,0x48a84832,0x4bd44bed,0x42944067,0x49cd4a2b,0x49824918,
0x4b874bb2,0x456a445d,0x48fd4969,0x4a4149e5,0x4b164b53,0x476f4670,0x4815488c,0x4ae14a95,0x4bfa4c00,0x3cce0000,0x4a3d4a99,0x49024887,
0x4bcc4be9,0x432840cb,0x496b49d8,0x49e34976,0x4b714ba4,0x45df44bd,0x487a48f6,0x4aa24a47,0x4aeb4b33,0x480546f9,0x46dd47ee,0x4b3a4af3,
0x4bf94c00,0x3d330000,0x49f44a5e,0x495848d8,0x4bc34be5,0x43ba412e,0x49024980,0x4a3d49d0,0x4b594b95,0x4654451d,0x47dd487c,0x4af74aa0,
0x4abd4b11,0x48504780,0x458146b5,0x4b834b43,0x4bf84c00,0x3d970000,0x49a64a1f,0x49aa4927,0x4bba4be1,0x44264191,0x48944922,0x4a904a23,
0x4b3f4b84,0x46c6457c,0x46bb47f9,0x4b424af0,0x4a8c4aed,0x48994802,0x441a4570,0x4bbc4b86,0x4bf74c00,0x3dfb0000,0x495449dc,0x49f84972,
0x4bb04bdc,0x446f41f4,0x482048bf,0x4adb4a71,0x4b244b72,0x473745da,0x458d46ee,0x4b814b36,0x4a584ac6,0x48e04842,0x41534420,0x4be34bbb,
0x4bf64c00,0x3e5f0000,0x48fd4996,0x4a4149ba,0x4ba54bd7,0x44b74257,0x474e4858,0x4b1e4ab8,0x4b074b5f,0x47a64637,0x445745da,0x4bb34b72,
0x4a214a9c,0x49244881,0x3cce4191,0x4bfa4be1,0x4bf54c00,0x3ec30000,0x48a3494d,0x4a8549fe,0x4b9a4bd2,0x44ff42b9,0x465447d8,0x4b594af9,
0x4ae84b4b,0x480a4693,0x423244bd,0x4bd94ba4,0x49e74a71,0x496648bf,0xb4523db0,0x4c004bf8,0x4bf34c00,0x3f270000,0x48454900,0x4ac44a3f,
0x4b8e4bcd,0x4546431b,0x455246f9,0x4b8b4b33,0x4ac74b36,0x484046ee,0x3f594334,0x4bf24bcb,0x49aa4a43,0x49a648fb,0xbef52a48,0x4bf44c00,
0x4bf24c00,0x3f8b0000,0x47c848b0,0x4afe4a7c,0x4b814bc7,0x458d437d,0x444b4614,0x4bb54b67,0x4aa54b20,0x48744748,0x388440e4,0x4bff4be8,
0x496b4a13,0x49e34935,0xc263bd4c,0x4bd74bf9,0x4bf04c00,0x3fef0000,0x46ff485d,0x4b324ab5,0x4b734bc1,0x45d443df,0x427c4529,0x4bd64b93,
0x4a814b08,0x48a847a1,0xb9b13d1a,0x4bfe4bf9,0x492949e1,0x4a1d496d,0xc49fc160,0x4ba94be3,0x4bef4c00,0x40290000,0x46314807,0x4b604ae9,
0x4b654bbb,0x461a4420,0x405b4438,0x4bed4bb7,0x4a5c4af0,0x48db47f9,0xbfef2e48,0x4bf04c00,0x48e549ad,0x4a5449a4,0xc602c408,0x4b6a4bbe,
0x4bed4c00,0x405b0000,0x455e475e,0x4b894b1a,0x4b574bb4,0x465f4451,0x3c6a4288,0x4bfb4bd5,0x4a354ad6,0x490c4828,0xc27cbc51,0x4bd64bfb,
0x489e4976,0x4a8949d8,0xc759c558,0x4b1b4b8a,0x4beb4c00,0x408d0000,0x448746aa,0x4bac4b46,0x4b474bad,0x46a44481,0x26484099,0x4c004beb,
0x4a0d4abc,0x493c4852,0xc47bc080,0x4bae4bec,0x4855493e,0x4aba4a0b,0xc850c69e,0x4abd4b49,0x4be94c00,0x40be0000,0x435945f1,0x4bc94b6e,
0x4b374ba6,0x46e844b1,0xbc383d4c,0x4bfc4bf9,0x49e34aa0,0x496b487c,0xc5b1c2d2,0x4b7a4bd1,0x480a4905,0x4ae84a3b,0xc8eac7d8,0x4a504af9,
0x4be74c00,0x40f00000,0x419e4534,0x4be04b91,0x4b274b9e,0x472c44e1,0xc042357f,0x4bee4c00,0x49b84a83,0x499948a6,0xc6ddc48d,0x4b3a4bab,
0x477a48c9,0x4b134a69,0xc979c881,0x49d64a9c,0x4be54c00,0x41220000,0x3fbd4475,0x4bf14baf,0x4b164b97,0x476f4511,0xc263b91b,0x4bd74bfe,
0x498b4a65,0x49c548ce,0xc7fec5ab,0x4aee4b7b,0x46dd488c,0x4b3a4a95,0xc9fcc90e,0x494f4a33,0x4be34c00,0x41530000,0x3c384365,0x4bfc4bc9,
0x4b044b8f,0x47b24540,0xc43ebe78,0x4bb74bf6,0x495d4a47,0x49f048f6,0xc889c6c1,0x4a974b41,0x463c484d,0x4b5e4abf,0xca73c992,0x48bc49be,
0x4be14c00,0x41850000,0x317f41db,0x4c004bdd,0x4af14b86,0x47f34570,0xc546c12e,0x4b8e4be5,0x492e4a27,0x4a19491d,0xc90cc7cd,0x4a354afc,
0x4599480d,0x4b7f4ae6,0xcadbca0b,0x4820493e,0x4bdf4c00,0x41b60000,0xb9b1404e,0x4bfe4bed,0x4ade4b7d,0x481a459f,0xc648c31b,0x4b5c4bcd,
0x48fd4a07,0x4a414943,0xc986c867,0x49c94aae,0x44f34796,0x4b9c4b0b,0xcb35ca78,0x46f448b5,0x4bdd4c00,0x41e80000,0xbe5f3d7e,0x4bf64bf8,
0x4acb4b74,0x483a45ce,0xc742c481,0x4b214bad,0x48cc49e5,0x4a674969,0xc9f8c8e2,0x49544a56,0x444b4710,0x4bb54b2e,0xcb7fcad9,0x45994822,
0x4bda4c00,0x42190000,0xc0f038b6,0x4be74bff,0x4ab64b6b,0x485a45fd,0xc81ac570,0x4ade4b86,0x489949c3,0x4a8c498d,0xca60c956,0x48d649f6,
0x43404687,0x4bcb4b4e,0xcbb8cb2e,0x44324710,0x4bd84c00,0x424b0000,0xc2adb248,0x4bd34c00,0x4aa24b62,0x487a462b,0xc88ec659,0x4a934b58,
0x4865499f,0x4ab049b1,0xcabdc9c3,0x4850498d,0x41e845fd,0x4bdd4b6b,0xcbe1cb74,0x418545ce,0x4bd64c00,0x427c0000,0xc432bbd9,0x4bb84bfc,
0x4a8c4b58,0x48994659,0xc8fdc73d,0x4a414b22,0x4830497b,0x4ad149d4,0xcb10ca27,0x4785491d,0x408d4570,0x4beb4b86,0xcbf9cbad,0x3d334481,
0x4bd34c00,0x42ad0000,0xc50bbf0e,0x4b984bf4,0x4a764b4e,0x48b74687,0xc966c80d,0x49e74ae6,0x47f34956,0x4af149f6,0xcb57ca83,0x465f48a6,
0x3e5f44e1,0x4bf64b9e,0xcc00cbd7,0xb17f4257,0x4bd04c00,0x42de0000,0xc5dfc115,0x4b714be6,0x4a604b43,0x48d646b5,0xc9c9c877,0x49864aa3,
0x47854930,0x4b104a17,0xcb92cad6,0x452f4828,0x3b434451,0x4bfd4bb4,0xcbf5cbf3,0xbe913f40,0x4bce4c00,0x430f0000,0xc6afc2a1,0x4b454bd4,
0x4a494b39,0x48f346e3,0xca25c8dd,0x491f4a5a,0x47154909,0x4b2c4a37,0xcbc0cb20,0x43eb4748,0x3311437d,0x4c004bc7,0xcbd9cbff,0xc2323711,
0x4bcb4c00,0x43400000,0xc77ac414,0x4b134bbc,0x4a314b2e,0x49114710,0xca7ac93e,0x48b24a0b,0x46a448e2,0x4b474a56,0xcbe2cb5f,0x416c4637,
0xb7764257,0x4bff4bd7,0xcbaccbfd,0xc487bb75,0x4bc84c00,0x43710000,0xc820c4d5,0x4adb4ba0,0x4a194b22,0x492e473d,0xcac7c99b,0x484049b5,
0x463148ba,0x4b604a74,0xcbf8cb95,0x3dc9451d,0xbc9c412e,0x4bfb4be5,0xcb6fcbeb,0xc5ebc099,0x4bc54c00,0x43a20000,0xc87fc593,0x4a9e4b80,
0x4a004b17,0x494a476a,0xcb0dc9f2,0x4790495b,0x45bc4891,0x4b784a92,0xcc00cbc0,0x317f43f7,0xbf594004,0x4bf24bf0,0xcb21cbca,0xc742c34c,
0x4bc24c00,0x43d30000,0xc8dbc64e,0x4a5c4b5a,0x49e74b0b,0x49664796,0xcb4aca43,0x469948fb,0x45464867,0x4b8e4aae,0xcbfbcbe0,0xbc6a41aa,
0xc1093db0,0x4be64bf8,0xcac4cb9b,0xc845c4f9,0x4bbf4c00,0x44020000,0xc933c705,0x4a154b30,0x49cd4aff,0x498247c2,0xcb7fca8e,0x45994896,
0x44cf483d,0x4ba14ac9,0xcbe9cbf5,0xc0be3eaa,0xc2633aac,0x4bd74bfd,0xca58cb5d,0xc8e0c642,0x4bbc4c00,0x441a0000,0xc986c7b7,0x49c94b02,
0x49b34af3,0x499d47ee,0xcbabcad3,0x4493482d,0x44574812,0x4bb34ae3,0xcbcbcbff,0xc34037da,0xc3ba33db,0x4bc34c00,0xc9dfcb11,0xc970c780,
0x4bb84c00,0x44320000,0xc9d6c832,0x49794ad0,0x49994ae6,0x49b8480d,0xcbcecb11,0x430f4780,0x43ba47cd,0x4bc34afc,0xcb9fcbfe,0xc4dbb97f,
0xc487b57f,0x4bac4c00,0xc958cab8,0xc9f4c858,0x4bb54c00,0x444b0000,0xca21c887,0x49244a99,0x497d4ad9,0x49d24822,0xcbe7cb49,0x40f0469e,
0x42c64775,0x4bd24b14,0xcb68cbf2,0xc60ebf72,0xc52fbb75,0x4b924bfd,0xc8c7ca52,0xca6bc8e7,0x4bb24c00,0x44630000,0xca67c8d8,0x48cc4a5e,
0x49624acc,0x49eb4838,0xcbf8cb79,0x3d9745b6,0x41cf471b,0x4bde4b2b,0xcb24cbdb,0xc737c20d,0xc5d4be14,0x4b734bf7,0xc82ac9e1,0xcad5c96d,
0x4bae4c00,0x447b0000,0xcaa9c927,0x486f4a1f,0x49464abf,0x4a04484d,0xcc00cba2,0x351b44c9,0x40d746c1,0x4be84b41,0xcad5cbb9,0xc82ac42c,
0xc676c036,0x4b524bee,0xc70ac964,0xcb2fc9e9,0x4bab4c00,0x44930000,0xcae5c972,0x480f49dc,0x49294ab1,0x4a1d4862,0xcbfecbc4,0xba1643ae,
0x3fbd4665,0x4bf14b55,0xca7acb8c,0xc8b2c54c,0xc715c160,0x4b2c4be3,0xc5b1c8dd,0xcb7aca5a,0x4ba74c00,0x44ab0000,0xcb1bc9ba,0x47594996,
0x490c4aa3,0x4a354877,0xcbf2cbdf,0xbf5941c3,0x3dc94608,0x4bf84b69,0xca15cb55,0xc933c665,0xc7b2c288,0x4b044bd5,0xc44bc84d,0xcbb5cabf,
0x4ba34c00,0x44c30000,0xcb4cc9fe,0x468d494d,0x48ee4a95,0x4a4d488c,0xcbdecbf1,0xc1cf3fa4,0x3ba745ab,0x4bfc4b7b,0xc9a6cb14,0xc9aac775,
0xc825c3ae,0x4ad84bc4,0xc1b6c76a,0xcbdfcb17,0x4b9f4c00,0x44db0000,0xcb78ca3f,0x45bc4900,0x48d14a87,0x4a6448a0,0xcbc0cbfd,0xc3eb3b75,
0x3776454c,0x4bff4b8c,0xc92ecac9,0xca19c83d,0xc86fc469,0x4aa94bb1,0xbd97c62b,0xcbf8cb62,0x4b9c4c00,0x44f30000,0xcb9eca7c,0x44e748b0,
0x48b24a78,0x4a7a48b5,0xcb9acc00,0xc4ffaa48,0xa64844ed,0x4c004b9d,0xc8adca74,0xca7ec8ba,0xc8b7c4f9,0x4a764b9b,0x2cb6c4e1,0xcc00cb9e,
0x4b984c00,0x450b0000,0xcbbdcab5,0x440e485d,0x48944a69,0x4a9048c9,0xcb6acbfc,0xc602bc1f,0xb81f448d,0x4bff4bab,0xc825ca17,0xcad8c930,
0xc8fdc587,0x4a414b82,0x3e2dc31b,0xcbf6cbcd,0x4b944c00,0x45230000,0xcbd7cae9,0x42634807,0x48744a5a,0x4aa548dd,0xcb32cbf0,0xc6ffc004,
0xbc06442c,0x4bfc4bb9,0xc72cc9b1,0xcb27c99f,0xc941c614,0x4a094b67,0x4201c067,0xcbdccbed,0x4b904c00,0x453a0000,0xcbeacb1a,0x40a6475e,
0x48554a4b,0x4aba48f1,0xcaf1cbdc,0xc7f3c1f4,0xbdfb4396,0x4bf74bc6,0xc602c943,0xcb6aca07,0xc982c69e,0x49cd4b49,0x446fbaac,0xcbb0cbfd,
0x4b8b4c00,0x45520000,0xcbf8cb46,0x3dc946aa,0x48354a3b,0x4ace4905,0xcaa9cbc1,0xc86fc3df,0xbfef42d2,0x4bf04bd1,0xc4cfc8ce,0xcba1ca65,
0xc9c0c726,0x49904b28,0x45d43852,0xcb73cbff,0x4b874c00,0x456a0000,0xcbffcb6e,0x388445f1,0x48154a2b,0x4ae14918,0xca58cb9e,0xc8e0c4e1,
0xc0f0420d,0x4be74bdb,0xc328c852,0xcbcccabc,0xc9fcc7ac,0x494f4b05,0x472c3fa4,0xcb27cbf1,0x4b834c00,0x45810000,0xcc00cb91,0xb51b4534,
0x47e84a1b,0x4af4492b,0xca00cb74,0xc94ac5ce,0xc1e84147,0x4bdd4be4,0xc0a6c7a1,0xcbeacb08,0xca35c817,0x490c4ae0,0x483a4288,0xcacbcbd5,
0x4b7f4c00,0x45990000,0xcbfacbaf,0xbcce4475,0x47a64a0b,0x4b07493e,0xc9a1cb43,0xc9afc6b5,0xc2de4080,0x4bd04bec,0xbc38c693,0xcbfccb4b,
0xca6bc858,0x48c74ab8,0x48d64499,0xca60cbaa,0x4b7a4c00,0x45b10000,0xcbefcbc9,0xc0294365,0x476449fa,0x4b184951,0xc93ccb0b,0xca0dc796,
0xc3d33f72,0x4bc24bf2,0x3311c57c,0xcc00cb84,0xca9ec896,0x487f4a8e,0x496645e5,0xc9e7cb70,0x4b764c00,0x45c80000,0xcbddcbdd,0xc1e841db,
0x472149e9,0x4b2a4964,0xc8d1cacc,0xca64c838,0xc4633de2,0x4bb24bf7,0x3dfbc45d,0xcbf7cbb2,0xcacec8d3,0x48354a62,0x49eb4726,0xc962cb28,
0x4b714c00,0x45df0000,0xcbc5cbed,0xc3a2404e,0x46dd49d8,0x4b3a4976,0xc85fca87,0xcab3c8a0,0xc4db3c51,0x4b9f4bfb,0x4185c26f,0xcbe1cbd6,
0xcafbc90e,0x47d24a33,0x4a64482d,0xc8d1cad3,0x4b6c4c00,0x45f70000,0xcba7cbf8,0xc4ab3d7e,0x469949c7,0x4b4a4989,0xc7d2ca3b,0xcafbc905,
0xc552397f,0x4b8b4bfe,0x4402c01d,0xcbbfcbef,0xcb24c948,0x47374a02,0x4ace48bf,0xc835ca71,0x4b684c00,0x460e0000,0xcb83cbff,0xc58138b6,
0x465449b5,0x4b59499b,0xc6ddc9e9,0xcb3ac964,0xc5c834b6,0x4b764c00,0x453abb11,0xcb90cbfd,0xcb4ac980,0x469949d0,0x4b2a4948,0xc721ca02,
0x2c002c00,0x2c002c00,0x2c002c00,0x2c002c00,0x2b642c00,0x261f29a8,0xa61f0000,0xab64a9a8,0x29a82c00,0xa9a80000,0xa9a8ac00,0x29a80000,
0x261f2c00,0xab64a9a8,0x2b640000,0xa61f29a8,0x2c00,0xac00,0x2c00,0xac00,0xa61f2c00,0x2b64a9a8,0xab640000,0x261f29a8,
0xa9a82c00,0x29a80000,0x29a8ac00,0xa9a80000,0xab642c00,0xa61f29a8,0x261f0000,0x2b64a9a8,0,0,0,0,
0x261f0000,0x2b6429a8,0x2b642c00,0x261f29a8,0x29a80000,0x29a82c00,0xa9a80000,0xa9a8ac00,0x2b640000,0xa61f29a8,0xa61fac00,0x2b6429a8,
0x2c000000,0xac000000,0x2c000000,0xac000000,0x2b640000,0xa61fa9a8,0xa61f2c00,0x2b64a9a8,0x29a80000,0x29a8ac00,0xa9a80000,0xa9a82c00,
0x261f0000,0x2b64a9a8,0x2b64ac00,0x261fa9a8,0xac002c00,0xac002c00,0xac002c00,0xac002c00,0xab642c00,0xa61f29a8,0x261f0000,0x2b64a9a8,
0xa9a82c00,0x29a80000,0x29a8ac00,0xa9a80000,0xa61f2c00,0x2b64a9a8,0xab640000,0x261f29a8,0x2c00,0xac00,0x2c00,0xac00,
0x261f2c00,0xab64a9a8,0x2b640000,0xa61f29a8,0x29a82c00,0xa9a80000,0xa9a8ac00,0x29a80000,0x2b642c00,0x261f29a8,0xa61f0000,0xab64a9a8,
0,0,0,0,0xa61f0000,0xab6429a8,0xab642c00,0xa61f29a8,0xa9a80000,0xa9a82c00,0x29a80000,0x29a8ac00,
0xab640000,0x261f29a8,0x261fac00,0xab6429a8,0xac000000,0x2c000000,0xac000000,0x2c000000,0xab640000,0x261fa9a8,0x261f2c00,0xab64a9a8,
0xa9a80000,0xa9a8ac00,0x29a80000,0x29a82c00,0xa61f0000,0xab64a9a8,0xab64ac00,0xa61fa9a8,0,0,0,0,
0xa61f0000,0xab64a9a8,0xab64ac00,0xa61fa9a8,0xa9a80000,0xa9a8ac00,0x29a80000,0x29a82c00,0xab640000,0x261fa9a8,0x261f2c00,0xab64a9a8,
0xac000000,0x2c000000,0xac000000,0x2c000000,0xab640000,0x261f29a8,0x261fac00,0xab6429a8,0xa9a80000,0xa9a82c00,0x29a80000,0x29a8ac00,
0xa61f0000,0xab6429a8,0xab642c00,0xa61f29a8,0x2c002c00,0x2c002c00,0x2c002c00,0x2c002c00,0x2b642c00,0x261f29a8,0xa61f0000,0xab64a9a8,
0x29a82c00,0xa9a80000,0xa9a8ac00,0x29a80000,0x261f2c00,0xab64a9a8,0x2b640000,0xa61f29a8,0x2c00,0xac00,0x2c00,0xac00,
0xa61f2c00,0x2b64a9a8,0xab640000,0x261f29a8,0xa9a82c00,0x29a80000,0x29a8ac00,0xa9a80000,0xab642c00,0xa61f29a8,0x261f0000,0x2b64a9a8,
0,0,0,0,0x261f0000,0x2b64a9a8,0x2b64ac00,0x261fa9a8,0x29a80000,0x29a8ac00,0xa9a80000,0xa9a82c00,
0x2b640000,0xa61fa9a8,0xa61f2c00,0x2b64a9a8,0x2c000000,0xac000000,0x2c000000,0xac000000,0x2b640000,0xa61f29a8,0xa61fac00,0x2b6429a8,
0x29a80000,0x29a82c00,0xa9a80000,0xa9a8ac00,0x261f0000,0x2b6429a8,0x2b642c00,0x261f29a8,0xac002c00,0xac002c00,0xac002c00,0xac002c00,
0xab642c00,0xa61f29a8,0x261f0000,0x2b64a9a8,0xa9a82c00,0x29a80000,0x29a8ac00,0xa9a80000,0xa61f2c00,0x2b64a9a8,0xab640000,0x261f29a8,
0x2c00,0xac00,0x2c00,0xac00,0x261f2c00,0xab64a9a8,0x2b640000,0xa61f29a8,0x29a82c00,0xa9a80000,0xa9a8ac00,0x29a80000,
0x2b642c00,0x261f29a8,0xa61f0000,0xab64a9a8,0x2c002c00,0x2c002c00,0x2c002c00,0x2c002c00,0xab64ac00,0xa61fa9a8,0x261f0000,0x2b6429a8,
0x29a82c00,0xa9a80000,0xa9a8ac00,0x29a80000,0xa61fac00,0x2b6429a8,0xab640000,0x261fa9a8,0x2c00,0xac00,0x2c00,0xac00,
0x261fac00,0xab6429a8,0x2b640000,0xa61fa9a8,0xa9a82c00,0x29a80000,0x29a8ac00,0xa9a80000,0x2b64ac00,0x261fa9a8,0xa61f0000,0xab6429a8,
0,0,0,0,0xa61f0000,0xab64a9a8,0xab64ac00,0xa61fa9a8,0x29a80000,0x29a82c00,0xa9a80000,0xa9a8ac00,
0xab640000,0x261fa9a8,0x261f2c00,0xab64a9a8,0x2c000000,0xac000000,0x2c000000,0xac000000,0xab640000,0x261f29a8,0x261fac00,0xab6429a8,
0x29a80000,0x29a8ac00,0xa9a80000,0xa9a82c00,0xa61f0000,0xab6429a8,0xab642c00,0xa61f29a8,0xac002c00,0xac002c00,0xac002c00,0xac002c00,
0x2b64ac00,0x261fa9a8,0xa61f0000,0xab6429a8,0xa9a82c00,0x29a80000,0x29a8ac00,0xa9a80000,0x261fac00,0xab6429a8,0x2b640000,0xa61fa9a8,
0x2c00,0xac00,0x2c00,0xac00,0xa61fac00,0x2b6429a8,0xab640000,0x261fa9a8,0x29a82c00,0xa9a80000,0xa9a8ac00,0x29a80000,
0xab64ac00,0xa61fa9a8,0x261f0000,0x2b6429a8,0,0,0,0,0x261f0000,0x2b64a9a8,0x2b64ac00,0x261fa9a8,
0xa9a80000,0xa9a82c00,0x29a80000,0x29a8ac00,0x2b640000,0xa61fa9a8,0xa61f2c00,0x2b64a9a8,0xac000000,0x2c000000,0xac000000,0x2c000000,
0x2b640000,0xa61f29a8,0xa61fac00,0x2b6429a8,0xa9a80000,0xa9a8ac00,0x29a80000,0x29a82c00,0x261f0000,0x2b6429a8,0x2b642c00,0x261f29a8,
0,0,0,0,0x261f0000,0x2b6429a8,0x2b642c00,0x261f29a8,0xa9a80000,0xa9a8ac00,0x29a80000,0x29a82c00,
0x2b640000,0xa61f29a8,0xa61fac00,0x2b6429a8,0xac000000,0x2c000000,0xac000000,0x2c000000,0x2b640000,0xa61fa9a8,0xa61f2c00,0x2b64a9a8,
0xa9a80000,0xa9a82c00,0x29a80000,0x29a8ac00,0x261f0000,0x2b64a9a8,0x2b64ac00,0x261fa9a8,0x2c002c00,0x2c002c00,0x2c002c00,0x2c002c00,
0xab64ac00,0xa61fa9a8,0x261f0000,0x2b6429a8,0x29a82c00,0xa9a80000,0xa9a8ac00,0x29a80000,0xa61fac00,0x2b6429a8,0xab640000,0x261fa9a8,
0x2c00,0xac00,0x2c00,0xac00,0x261fac00,0xab6429a8,0x2b640000,0xa61fa9a8,0xa9a82c00,0x29a80000,0x29a8ac00,0xa9a80000,
0x2b64ac00,0x261fa9a8,0xa61f0000,0xab6429a8,0,0,0,0,0xa61f0000,0xab6429a8,0xab642c00,0xa61f29a8,
0x29a80000,0x29a8ac00,0xa9a80000,0xa9a82c00,0xab640000,0x261f29a8,0x261fac00,0xab6429a8,0x2c000000,0xac000000,0x2c000000,0xac000000,
0xab640000,0x261fa9a8,0x261f2c00,0xab64a9a8,0x29a80000,0x29a82c00,0xa9a80000,0xa9a8ac00,0xa61f0000,0xab64a9a8,0xab64ac00,0xa61fa9a8,
0xac002c00,0xac002c00,0xac002c00,0xac002c00,0x2b64ac00,0x261fa9a8,0xa61f0000,0xab6429a8,0xa9a82c00,0x29a80000,0x29a8ac00,0xa9a80000,
0x261fac00,0xab6429a8,0x2b640000,0xa61fa9a8,0x2c00,0xac00,0x2c00,0xac00,0xa61fac00,0x2b6429a8,0xab640000,0x261fa9a8,
0x29a82c00,0xa9a80000,0xa9a8ac00,0x29a80000,0xab64ac00,0xa61fa9a8,0x261f0000,0x2b6429a8,0x2bd92c00,0x2aa72b64,0x287229a8,0x223e261f,
0x2aa72c00,0xa23e261f,0xabd9a9a8,0xa872ab64,0x28722c00,0xabd9a61f,0x223ea9a8,0x2aa72b64,0x223e2c00,0xa872ab64,0x2aa729a8,0xabd9a61f,
0xa23e2c00,0x2872ab64,0xaaa729a8,0x2bd9a61f,0xa8722c00,0x2bd9a61f,0xa23ea9a8,0xaaa72b64,0xaaa72c00,0x223e261f,0x2bd9a9a8,0x2872ab64,
0xabd92c00,0xaaa72b64,0xa87229a8,0xa23e261f,0x223e0000,0x2872261f,0x2aa729a8,0x2bd92b64,0x28720000,0x2bd92b64,0x223e29a8,0xaaa7a61f,
0x2aa70000,0x223e2b64,0xabd9a9a8,0x2872a61f,0x2bd90000,0xaaa7261f,0x2872a9a8,0xa23e2b64,0x2bd90000,0xaaa7a61f,0x287229a8,0xa23eab64,
0x2aa70000,0x223eab64,0xabd929a8,0x2872261f,0x28720000,0x2bd9ab64,0x223ea9a8,0xaaa7261f,0x223e0000,0x2872a61f,0x2aa7a9a8,0x2bd9ab64,
0xabd92c00,0xaaa72b64,0xa87229a8,0xa23e261f,0xaaa72c00,0x223e261f,0x2bd9a9a8,0x2872ab64,0xa8722c00,0x2bd9a61f,0xa23ea9a8,0xaaa72b64,
0xa23e2c00,0x2872ab64,0xaaa729a8,0x2bd9a61f,0x223e2c00,0xa872ab64,0x2aa729a8,0xabd9a61f,0x28722c00,0xabd9a61f,0x223ea9a8,0x2aa72b64,
0x2aa72c00,0xa23e261f,0xabd9a9a8,0xa872ab64,0x2bd92c00,0x2aa72b64,0x287229a8,0x223e261f,0xa23e0000,0xa872261f,0xaaa729a8,0xabd92b64,
0xa8720000,0xabd92b64,0xa23e29a8,0x2aa7a61f,0xaaa70000,0xa23e2b64,0x2bd9a9a8,0xa872a61f,0xabd90000,0x2aa7261f,0xa872a9a8,0x223e2b64,
0xabd90000,0x2aa7a61f,0xa87229a8,0x223eab64,0xaaa70000,0xa23eab64,0x2bd929a8,0xa872261f,0xa8720000,0xabd9ab64,0xa23ea9a8,0x2aa7261f,
0xa23e0000,0xa872a61f,0xaaa7a9a8,0xabd9ab64,0xa23e0000,0xa872a61f,0xaaa7a9a8,0xabd9ab64,0xa8720000,0xabd9ab64,0xa23ea9a8,0x2aa7261f,
0xaaa70000,0xa23eab64,0x2bd929a8,0xa872261f,0xabd90000,0x2aa7a61f,0xa87229a8,0x223eab64,0xabd90000,0x2aa7261f,0xa872a9a8,0x223e2b64,
0xaaa70000,0xa23e2b64,0x2bd9a9a8,0xa872a61f,0xa8720000,0xabd92b64,0xa23e29a8,0x2aa7a61f,0xa23e0000,0xa872261f,0xaaa729a8,0xabd92b64,
0x2bd92c00,0x2aa72b64,0x287229a8,0x223e261f,0x2aa72c00,0xa23e261f,0xabd9a9a8,0xa872ab64,0x28722c00,0xabd9a61f,0x223ea9a8,0x2aa72b64,
0x223e2c00,0xa872ab64,0x2aa729a8,0xabd9a61f,0xa23e2c00,0x2872ab64,0xaaa729a8,0x2bd9a61f,0xa8722c00,0x2bd9a61f,0xa23ea9a8,0xaaa72b64,
0xaaa72c00,0x223e261f,0x2bd9a9a8,0x2872ab64,0xabd92c00,0xaaa72b64,0xa87229a8,0xa23e261f,0x223e0000,0x2872a61f,0x2aa7a9a8,0x2bd9ab64,
0x28720000,0x2bd9ab64,0x223ea9a8,0xaaa7261f,0x2aa70000,0x223eab64,0xabd929a8,0x2872261f,0x2bd90000,0xaaa7a61f,0x287229a8,0xa23eab64,
0x2bd90000,0xaaa7261f,0x2872a9a8,0xa23e2b64,0x2aa70000,0x223e2b64,0xabd9a9a8,0x2872a61f,0x28720000,0x2bd92b64,0x223e29a8,0xaaa7a61f,
0x223e0000,0x2872261f,0x2aa729a8,0x2bd92b64,0xabd92c00,0xaaa72b64,0xa87229a8,0xa23e261f,0xaaa72c00,0x223e261f,0x2bd9a9a8,0x2872ab64,
0xa8722c00,0x2bd9a61f,0xa23ea9a8,0xaaa72b64,0xa23e2c00,0x2872ab64,0xaaa729a8,0x2bd9a61f,0x223e2c00,0xa872ab64,0x2aa729a8,0xabd9a61f,
0x28722c00,0xabd9a61f,0x223ea9a8,0x2aa72b64,0x2aa72c00,0xa23e261f,0xabd9a9a8,0xa872ab64,0x2bd92c00,0x2aa72b64,0x287229a8,0x223e261f,
0xa23e0000,0xa872a61f,0xaaa7a9a8,0xabd9ab64,0x28720000,0x2bd92b64,0x223e29a8,0xaaa7a61f,0xaaa70000,0xa23eab64,0x2bd929a8,0xa872261f,
0x2bd90000,0xaaa7261f,0x2872a9a8,0xa23e2b64,0xabd90000,0x2aa7261f,0xa872a9a8,0x223e2b64,0x2aa70000,0x223eab64,0xabd929a8,0x2872261f,
0xa8720000,0xabd92b64,0xa23e29a8,0x2aa7a61f,0x223e0000,0x2872a61f,0x2aa7a9a8,0x2bd9ab64,0x2bd92c00,0x2aa72b64,0x287229a8,0x223e261f,
0xaaa7ac00,0x223ea61f,0x2bd929a8,0x28722b64,0x28722c00,0xabd9a61f,0x223ea9a8,0x2aa72b64,0xa23eac00,0x28722b64,0xaaa7a9a8,0x2bd9261f,
0xa23e2c00,0x2872ab64,0xaaa729a8,0x2bd9a61f,0x2872ac00,0xabd9261f,0x223e29a8,0x2aa7ab64,0xaaa72c00,0x223e261f,0x2bd9a9a8,0x2872ab64,
0x2bd9ac00,0x2aa7ab64,0x2872a9a8,0x223ea61f,0x223e0000,0x2872a61f,0x2aa7a9a8,0x2bd9ab64,0xa8720000,0xabd92b64,0xa23e29a8,0x2aa7a61f,
0x2aa70000,0x223eab64,0xabd929a8,0x2872261f,0xabd90000,0x2aa7261f,0xa872a9a8,0x223e2b64,0x2bd90000,0xaaa7261f,0x2872a9a8,0xa23e2b64,
0xaaa70000,0xa23eab64,0x2bd929a8,0xa872261f,0x28720000,0x2bd92b64,0x223e29a8,0xaaa7a61f,0xa23e0000,0xa872a61f,0xaaa7a9a8,0xabd9ab64,
0xabd92c00,0xaaa72b64,0xa87229a8,0xa23e261f,0x2aa7ac00,0xa23ea61f,0xabd929a8,0xa8722b64,0xa8722c00,0x2bd9a61f,0xa23ea9a8,0xaaa72b64,
0x223eac00,0xa8722b64,0x2aa7a9a8,0xabd9261f,0x223e2c00,0xa872ab64,0x2aa729a8,0xabd9a61f,0xa872ac00,0x2bd9261f,0xa23e29a8,0xaaa7ab64,
0x2aa72c00,0xa23e261f,0xabd9a9a8,0xa872ab64,0xabd9ac00,0xaaa7ab64,0xa872a9a8,0xa23ea61f,0xabd9ac00,0xaaa7ab64,0xa872a9a8,0xa23ea61f,
0x2aa72c00,0xa23e261f,0xabd9a9a8,0xa872ab64,0xa872ac00,0x2bd9261f,0xa23e29a8,0xaaa7ab64,0x223e2c00,0xa872ab64,0x2aa729a8,0xabd9a61f,
0x223eac00,0xa8722b64,0x2aa7a9a8,0xabd9261f,0xa8722c00,0x2bd9a61f,0xa23ea9a8,0xaaa72b64,0x2aa7ac00,0xa23ea61f,0xabd929a8,0xa8722b64,
0xabd92c00,0xaaa72b64,0xa87229a8,0xa23e261f,0xa23e0000,0xa872a61f,0xaaa7a9a8,0xabd9ab64,0x28720000,0x2bd92b64,0x223e29a8,0xaaa7a61f,
0xaaa70000,0xa23eab64,0x2bd929a8,0xa872261f,0x2bd90000,0xaaa7261f,0x2872a9a8,0xa23e2b64,0xabd90000,0x2aa7261f,0xa872a9a8,0x223e2b64,
0x2aa70000,0x223eab64,0xabd929a8,0x2872261f,0xa8720000,0xabd92b64,0xa23e29a8,0x2aa7a61f,0x223e0000,0x2872a61f,0x2aa7a9a8,0x2bd9ab64,
0x2bd9ac00,0x2aa7ab64,0x2872a9a8,0x223ea61f,0xaaa72c00,0x223e261f,0x2bd9a9a8,0x2872ab64,0x2872ac00,0xabd9261f,0x223e29a8,0x2aa7ab64,
0xa23e2c00,0x2872ab64,0xaaa729a8,0x2bd9a61f,0xa23eac00,0x28722b64,0xaaa7a9a8,0x2bd9261f,0x28722c00,0xabd9a61f,0x223ea9a8,0x2aa72b64,
0xaaa7ac00,0x223ea61f,0x2bd929a8,0x28722b64,0x2bd92c00,0x2aa72b64,0x287229a8,0x223e261f,0x223e0000,0x2872a61f,0x2aa7a9a8,0x2bd9ab64,
0xa8720000,0xabd92b64,0xa23e29a8,0x2aa7a61f,0x2aa70000,0x223eab64,0xabd929a8,0x2872261f,0xabd90000,0x2aa7261f,0xa872a9a8,0x223e2b64,
0x2bd90000,0xaaa7261f,0x2872a9a8,0xa23e2b64,0xaaa70000,0xa23eab64,0x2bd929a8,0xa872261f,0x28720000,0x2bd92b64,0x223e29a8,0xaaa7a61f,
0xa23e0000,0xa872a61f,0xaaa7a9a8,0xabd9ab64,0x27fe2800,0x96480000,0x273b2764,0xa2d7a21f,0x27ea27f6,0x9cb29a46,0x26dd270e,0xa41da38b,
0x27c327d9,0x9fc69e3e,0x266d26a7,0xa4c4a472,0x278827a8,0xa164a0a5,0x25ed262f,0xa55fa513,0x27c32800,0x9fc60000,0xa4c4a21f,0xa66da764,
0x25ed270e,0xa55fa38b,0xa73ba62f,0xa2d7a513,0x21642472,0xa788a6a7,0xa7fea7d9,0x16489e3e,0x9cb21a46,0xa7eaa7f6,0xa6dda7a8,0x241d20a5,
0x273b2800,0xa2d70000,0xa55fa764,0x25ed221f,0x1fc62513,0xa7c3a62f,0x1cb2a0a5,0x27ea27a8,0xa4c49e3e,0xa66da7d9,0x26dd2472,0x241d26a7,
0xa7fea70e,0x9648a38b,0x278827f6,0xa1641a46,0x266d2800,0xa4c40000,0x26dd221f,0x241d2764,0xa16420a5,0xa788a7a8,0x25ed27f6,0xa55f9a46,
0xa7fea6a7,0x1648a472,0xa2d71e3e,0xa73ba7d9,0x9fc6a62f,0x27c32513,0xa7eaa70e,0x1cb2a38b,0x255f2800,0xa5ed0000,0x21642764,0xa788a21f,
0xa66d9a46,0xa4c4a7f6,0xa7c3a38b,0x9fc6a70e,0xa41da7d9,0x26dd1e3e,0x9cb2a6a7,0x27ea2472,0x273b20a5,0x22d727a8,0x27fe2513,0x1648262f,
0x241d2800,0xa6dd0000,0xa7eaa21f,0x9cb2a764,0xa7fea38b,0x9648a70e,0x2164a513,0x2788262f,0x22d7a472,0x273b26a7,0x255f27d9,0xa5ed1e3e,
0x24c427f6,0xa66d1a46,0xa7c3a0a5,0x9fc6a7a8,0x21642800,0xa7880000,0x1648a764,0x27fe221f,0xa6dda62f,0x241da513,0x24c427a8,0xa66d20a5,
0x27ea1e3e,0x1cb227d9,0xa7c3a472,0x1fc6a6a7,0xa55f238b,0xa5eda70e,0x273b9a46,0x22d727f6,0x1cb22800,0xa7ea0000,0x27c3221f,0x9fc62764,
0xa2d7a7a8,0x273ba0a5,0xa7fe9a46,0x9648a7f6,0x255f26a7,0xa5ed2472,0x27889e3e,0x216427d9,0xa6dda513,0x241da62f,0xa66d238b,0xa4c4a70e,
0x96482800,0xa7fe0000,0xa2d72764,0xa73ba21f,0x1cb2a7f6,0x27ea1a46,0x241da70e,0x26dd238b,0x9fc627d9,0xa7c39e3e,0xa4c426a7,0xa66da472,
0x2164a7a8,0x278820a5,0x255fa62f,0x25ed2513,0x9fc62800,0xa7c30000,0xa66da21f,0x24c4a764,0x255fa70e,0x25ed238b,0x22d7262f,0xa73b2513,
0xa7882472,0xa164a6a7,0x1648a7d9,0x27fe9e3e,0x27ea9a46,0x9cb227f6,0xa41d27a8,0xa6dda0a5,0xa2d72800,0xa73b0000,0x25eda764,0x255f221f,
0x27c3a513,0x1fc6262f,0xa7ea20a5,0x1cb2a7a8,0xa66d9e3e,0x24c4a7d9,0x241d2472,0xa6dd26a7,0x1648270e,0xa7fe238b,0x2164a7f6,0x27889a46,
0xa4c42800,0xa66d0000,0x241d221f,0xa6dd2764,0x2788a0a5,0xa16427a8,0x255fa7f6,0x25ed1a46,0x1648a6a7,0x27fea472,0xa73b1e3e,0x22d7a7d9,
0xa7c3262f,0x9fc6a513,0x9cb2270e,0xa7ea238b,0xa5ed2800,0xa55f0000,0xa7882764,0xa164a21f,0x24c41a46,0xa66d27f6,0x1fc6238b,0xa7c3270e,
0x26dda7d9,0x241d1e3e,0x27eaa6a7,0x1cb22472,0xa2d7a0a5,0x273ba7a8,0x9648a513,0x27fea62f,0xa6dd2800,0xa41d0000,0x9cb2a21f,0x27eaa764,
0x1648238b,0xa7fe270e,0xa7882513,0x2164a62f,0x273ba472,0xa2d726a7,0xa5ed27d9,0xa55f1e3e,0x266da7f6,0x24c49a46,0x1fc620a5,0xa7c327a8,
0xa7882800,0xa1640000,0x27fea764,0x9648221f,0xa41d262f,0xa6dd2513,0x266da7a8,0x24c4a0a5,0x1cb21e3e,0xa7ea27d9,0x1fc6a472,0x27c3a6a7,
0x25eda38b,0xa55f270e,0xa2d71a46,0x273ba7f6,0xa7ea2800,0x9cb20000,0x9fc6221f,0xa7c32764,0xa73b27a8,0xa2d720a5,0x16481a46,0xa7fe27f6,
0xa5ed26a7,0xa55f2472,0x21649e3e,0xa78827d9,0xa41d2513,0xa6dd262f,0x24c4a38b,0xa66d270e,0xa7fe2800,0x16480000,0xa73b2764,0x22d7a21f,
0xa7ea27f6,0x1cb29a46,0xa6dd270e,0x241da38b,0xa7c327d9,0x1fc69e3e,0xa66d26a7,0x24c4a472,0xa78827a8,0x2164a0a5,0xa5ed262f,0x255fa513,
0xa7c32800,0x1fc60000,0x24c4a21f,0x266da764,0xa5ed270e,0x255fa38b,0x273ba62f,0x22d7a513,0xa1642472,0x2788a6a7,0x27fea7d9,0x96489e3e,
0x1cb21a46,0x27eaa7f6,0x26dda7a8,0xa41d20a5,0xa73b2800,0x22d70000,0x255fa764,0xa5ed221f,0x9fc62513,0x27c3a62f,0x9cb2a0a5,0xa7ea27a8,
0x24c49e3e,0x266da7d9,0xa6dd2472,0xa41d26a7,0x27fea70e,0x1648a38b,0xa78827f6,0x21641a46,0xa66d2800,0x24c40000,0xa6dd221f,0xa41d2764,
0x216420a5,0x2788a7a8,0xa5ed27f6,0x255f9a46,0x27fea6a7,0x9648a472,0x22d71e3e,0x273ba7d9,0x1fc6a62f,0xa7c32513,0x27eaa70e,0x9cb2a38b,
0xa55f2800,0x25ed0000,0xa1642764,0x2788a21f,0x266d9a46,0x24c4a7f6,0x27c3a38b,0x1fc6a70e,0x241da7d9,0xa6dd1e3e,0x1cb2a6a7,0xa7ea2472,
0xa73b20a5,0xa2d727a8,0xa7fe2513,0x9648262f,0xa41d2800,0x26dd0000,0x27eaa21f,0x1cb2a764,0x27fea38b,0x1648a70e,0xa164a513,0xa788262f,
0xa2d7a472,0xa73b26a7,0xa55f27d9,0x25ed1e3e,0xa4c427f6,0x266d1a46,0x27c3a0a5,0x1fc6a7a8,0xa1642800,0x27880000,0x9648a764,0xa7fe221f,
0x26dda62f,0xa41da513,0xa4c427a8,0x266d20a5,0xa7ea1e3e,0x9cb227d9,0x27c3a472,0x9fc6a6a7,0x255f238b,0x25eda70e,0xa73b9a46,0xa2d727f6,
0x9cb22800,0x27ea0000,0xa7c3221f,0x1fc62764,0x22d7a7a8,0xa73ba0a5,0x27fe9a46,0x1648a7f6,0xa55f26a7,0x25ed2472,0xa7889e3e,0xa16427d9,
0x26dda513,0xa41da62f,0x266d238b,0x24c4a70e,0x16482800,0x27fe0000,0x22d72764,0x273ba21f,0x9cb2a7f6,0xa7ea1a46,0xa41da70e,0xa6dd238b,
0x1fc627d9,0x27c39e3e,0x24c426a7,0x266da472,0xa164a7a8,0xa78820a5,0xa55fa62f,0xa5ed2513,0x1fc62800,0x27c30000,0x266da21f,0xa4c4a764,
0xa55fa70e,0xa5ed238b,0xa2d7262f,0x273b2513,0x27882472,0x2164a6a7,0x9648a7d9,0xa7fe9e3e,0xa7ea9a46,0x1cb227f6,0x241d27a8,0x26dda0a5,
0x22d72800,0x273b0000,0xa5eda764,0xa55f221f,0xa7c3a513,0x9fc6262f,0x27ea20a5,0x9cb2a7a8,0x266d9e3e,0xa4c4a7d9,0xa41d2472,0x26dd26a7,
0x9648270e,0x27fe238b,0xa164a7f6,0xa7889a46,0x24c42800,0x266d0000,0xa41d221f,0x26dd2764,0xa788a0a5,0x216427a8,0xa55fa7f6,0xa5ed1a46,
0x9648a6a7,0xa7fea472,0x273b1e3e,0xa2d7a7d9,0x27c3262f,0x1fc6a513,0x1cb2270e,0x27ea238b,0x25ed2800,0x255f0000,0x27882764,0x2164a21f,
0xa4c41a46,0x266d27f6,0x9fc6238b,0x27c3270e,0xa6dda7d9,0xa41d1e3e,0xa7eaa6a7,0x9cb22472,0x22d7a0a5,0xa73ba7a8,0x1648a513,0xa7fea62f,
0x26dd2800,0x241d0000,0x1cb2a21f,0xa7eaa764,0x9648238b,0x27fe270e,0x27882513,0xa164a62f,0xa73ba472,0x22d726a7,0x25ed27d9,0x255f1e3e,
0xa66da7f6,0xa4c49a46,0x9fc620a5,0x27c327a8,0x27882800,0x21640000,0xa7fea764,0x1648221f,0x241d262f,0x26dd2513,0xa66da7a8,0xa4c4a0a5,
0x9cb21e3e,0x27ea27d9,0x9fc6a472,0xa7c3a6a7,0xa5eda38b,0x255f270e,0x22d71a46,0xa73ba7f6,0x27ea2800,0x1cb20000,0x1fc6221f,0x27c32764,
0x273b27a8,0x22d720a5,0x96481a46,0x27fe27f6,0x25ed26a7,0x255f2472,0xa1649e3e,0x278827d9,0x241d2513,0x26dd262f,0xa4c4a38b,0x266d270e,
0x255f25a8,0xa5eda5a8,0x2164221f,0xa788a764,0x24c42513,0xa66da62f,0x1fc620a5,0xa7c3a7a8,0x241d2472,0xa6dda6a7,0x1cb21e3e,0xa7eaa7d9,
0x22d7238b,0xa73ba70e,0x16481a46,0xa7fea7f6,0xa41da5a8,0x26dd25a8,0x27ea2764,0x1cb2221f,0x9648a0a5,0x27fe27a8,0x278827f6,0xa1649a46,
0x22d71e3e,0x273b27d9,0x255f26a7,0xa5eda472,0x266d2513,0x24c4262f,0x1fc6238b,0xa7c3a70e,0x216425a8,0xa788a5a8,0x1648a21f,0x27fe2764,
0xa41d9a46,0xa6dda7f6,0x266d238b,0x24c4270e,0xa7eaa6a7,0x9cb2a472,0x27c327d9,0x9fc61e3e,0xa5eda7a8,0x255f20a5,0x22d7262f,0xa73ba513,
0x9cb2a5a8,0x27ea25a8,0xa7c3a764,0x1fc6a21f,0x273b238b,0x22d7270e,0x9648a513,0x27fe262f,0x255f27d9,0xa5ed9e3e,0x27882472,0x216426a7,
0xa41d1a46,0xa6dda7f6,0x24c427a8,0xa66da0a5,0x964825a8,0xa7fea5a8,0xa2d7221f,0xa73ba764,0xa7eaa62f,0x1cb2a513,0xa6dda7a8,0x241da0a5,
0x1fc6a472,0x27c326a7,0x24c49e3e,0x266d27d9,0x2788270e,0xa164238b,0x25ed27f6,0xa55f1a46,0x1fc6a5a8,0x27c325a8,0x266d2764,0xa4c4221f,
0x25ed27a8,0xa55f20a5,0xa73b9a46,0xa2d7a7f6,0xa7889e3e,0xa164a7d9,0x1648a6a7,0x27fe2472,0x1cb2a62f,0x27ea2513,0x26dd270e,0xa41d238b,
0xa2d725a8,0xa73ba5a8,0x25eda21f,0x255f2764,0x9fc6a7f6,0x27c31a46,0x9cb2270e,0xa7eaa38b,0x266d26a7,0xa4c42472,0xa41da7d9,0x26dd9e3e,
0xa7fea0a5,0x9648a7a8,0x27882513,0xa164262f,0x24c4a5a8,0x266d25a8,0xa41da764,0x26dda21f,0xa164270e,0xa788a38b,0x25ed262f,0xa55f2513,
0x1648a7d9,0x27fe1e3e,0xa73ba472,0x22d7a6a7,0x1fc627f6,0xa7c31a46,0x27ea20a5,0x9cb227a8,0xa5ed25a8,0xa55fa5a8,0xa788221f,0xa164a764,
0x266da513,0x24c4262f,0x27c3a0a5,0x1fc627a8,0xa6dd2472,0xa41da6a7,0xa7ea1e3e,0x9cb2a7d9,0x273ba38b,0x22d7270e,0x27fe9a46,0x164827f6,
0x26dda5a8,0x241d25a8,0x1cb22764,0xa7ea221f,0xa7fe20a5,0x9648a7a8,0x2164a7f6,0x27881a46,0x273b1e3e,0xa2d727d9,0xa5ed26a7,0xa55fa472,
0xa4c4a513,0x266da62f,0x27c3a38b,0x1fc6270e,0xa78825a8,0xa164a5a8,0x27fea21f,0x96482764,0x26dd1a46,0xa41d27f6,0xa4c4a38b,0x266da70e,
0x9cb2a6a7,0x27eaa472,0x9fc627d9,0xa7c31e3e,0xa55f27a8,0xa5eda0a5,0x273ba62f,0x22d72513,0x27eaa5a8,0x1cb225a8,0x1fc6a764,0x27c3a21f,
0xa2d7a38b,0x273ba70e,0xa7fe2513,0x9648a62f,0xa5ed27d9,0xa55f9e3e,0x21642472,0xa78826a7,0x26dd9a46,0xa41d27f6,0x266da7a8,0x24c420a5,
0xa7fe25a8,0x1648a5a8,0xa73b221f,0x22d7a764,0x9cb2262f,0xa7ea2513,0xa41d27a8,0xa6dd20a5,0x27c3a472,0x9fc626a7,0x266d9e3e,0xa4c427d9,
0x2164a70e,0x2788a38b,0x255fa7f6,0x25ed9a46,0x27c3a5a8,0x9fc625a8,0xa4c42764,0xa66d221f,0x255fa7a8,0x25eda0a5,0x22d71a46,0xa73b27f6,
0xa1649e3e,0x2788a7d9,0x27fea6a7,0x96482472,0xa7ea262f,0x1cb2a513,0x241da70e,0x26dda38b,0xa73b25a8,0x22d7a5a8,0x255fa21f,0xa5ed2764,
0xa7c327f6,0x9fc69a46,0x27eaa70e,0x9cb2238b,0xa4c426a7,0xa66d2472,0x26dda7d9,0x241d9e3e,0x164820a5,0xa7fe27a8,0x2164a513,0x2788a62f,
0x266da5a8,0xa4c425a8,0x26dda764,0x241da21f,0x2788a70e,0xa164238b,0x255fa62f,0x25eda513,0x27fea7d9,0x96481e3e,0x22d7a472,0x273ba6a7,
0x27c3a7f6,0x1fc69a46,0x1cb2a0a5,0x27eaa7a8,0xa55f25a8,0x25eda5a8,0xa164221f,0x2788a764,0xa4c42513,0x266da62f,0x9fc620a5,0x27c3a7a8,
0xa41d2472,0x26dda6a7,0x9cb21e3e,0x27eaa7d9,0xa2d7238b,0x273ba70e,0x96481a46,0x27fea7f6,0x241da5a8,0xa6dd25a8,0xa7ea2764,0x9cb2221f,
0x1648a0a5,0xa7fe27a8,0xa78827f6,0x21649a46,0xa2d71e3e,0xa73b27d9,0xa55f26a7,0x25eda472,0xa66d2513,0xa4c4262f,0x9fc6238b,0x27c3a70e,
0xa16425a8,0x2788a5a8,0x9648a21f,0xa7fe2764,0x241d9a46,0x26dda7f6,0xa66d238b,0xa4c4270e,0x27eaa6a7,0x1cb2a472,0xa7c327d9,0x1fc61e3e,
0x25eda7a8,0xa55f20a5,0xa2d7262f,0x273ba513,0x1cb2a5a8,0xa7ea25a8,0x27c3a764,0x9fc6a21f,0xa73b238b,0xa2d7270e,0x1648a513,0xa7fe262f,
0xa55f27d9,0x25ed9e3e,0xa7882472,0xa16426a7,0x241d1a46,0x26dda7f6,0xa4c427a8,0x266da0a5,0x164825a8,0x27fea5a8,0x22d7221f,0x273ba764,
0x27eaa62f,0x9cb2a513,0x26dda7a8,0xa41da0a5,0x9fc6a472,0xa7c326a7,0xa4c49e3e,0xa66d27d9,0xa788270e,0x2164238b,0xa5ed27f6,0x255f1a46,
0x9fc6a5a8,0xa7c325a8,0xa66d2764,0x24c4221f,0xa5ed27a8,0x255f20a5,0x273b9a46,0x22d7a7f6,0x27889e3e,0x2164a7d9,0x9648a6a7,0xa7fe2472,
0x9cb2a62f,0xa7ea2513,0xa6dd270e,0x241d238b,0x22d725a8,0x273ba5a8,0xa5eda21f,0xa55f2764,0x1fc6a7f6,0xa7c31a46,0x1cb2270e,0x27eaa38b,
0xa66d26a7,0x24c42472,0x241da7d9,0xa6dd9e3e,0x27fea0a5,0x1648a7a8,0xa7882513,0x2164262f,0xa4c4a5a8,0xa66d25a8,0x241da764,0xa6dda21f,
0x2164270e,0x2788a38b,0xa5ed262f,0x255f2513,0x9648a7d9,0xa7fe1e3e,0x273ba472,0xa2d7a6a7,0x9fc627f6,0x27c31a46,0xa7ea20a5,0x1cb227a8,
0x25ed25a8,0x255fa5a8,0x2788221f,0x2164a764,0xa66da513,0xa4c4262f,0xa7c3a0a5,0x9fc627a8,0x26dd2472,0x241da6a7,0x27ea1e3e,0x1cb2a7d9,
0xa73ba38b,0xa2d7270e,0xa7fe9a46,0x964827f6,0xa6dda5a8,0xa41d25a8,0x9cb22764,0x27ea221f,0x27fe20a5,0x1648a7a8,0xa164a7f6,0xa7881a46,
0xa73b1e3e,0x22d727d9,0x25ed26a7,0x255fa472,0x24c4a513,0xa66da62f,0xa7c3a38b,0x9fc6270e,0x278825a8,0x2164a5a8,0xa7fea21f,0x16482764,
0xa6dd1a46,0x241d27f6,0x24c4a38b,0xa66da70e,0x1cb2a6a7,0xa7eaa472,0x1fc627d9,0x27c31e3e,0x255f27a8,0x25eda0a5,0xa73ba62f,0xa2d72513,
0xa7eaa5a8,0x9cb225a8,0x9fc6a764,0xa7c3a21f,0x22d7a38b,0xa73ba70e,0x27fe2513,0x1648a62f,0x25ed27d9,0x255f9e3e,0xa1642472,0x278826a7,
0xa6dd9a46,0x241d27f6,0xa66da7a8,0xa4c420a5,0x27fe25a8,0x9648a5a8,0x273b221f,0xa2d7a764,0x1cb2262f,0x27ea2513,0x241d27a8,0x26dd20a5,
0xa7c3a472,0x1fc626a7,0xa66d9e3e,0x24c427d9,0xa164a70e,0xa788a38b,0xa55fa7f6,0xa5ed9a46,0xa7c3a5a8,0x1fc625a8,0x24c42764,0x266d221f,
0xa55fa7a8,0xa5eda0a5,0xa2d71a46,0x273b27f6,0x21649e3e,0xa788a7d9,0xa7fea6a7,0x16482472,0x27ea262f,0x9cb2a513,0xa41da70e,0xa6dda38b,
0x273b25a8,0xa2d7a5a8,0xa55fa21f,0x25ed2764,0x27c327f6,0x1fc69a46,0xa7eaa70e,0x1cb2238b,0x24c426a7,0x266d2472,0xa6dda7d9,0xa41d9e3e,
0x964820a5,0x27fe27a8,0xa164a513,0xa788a62f,0xa66da5a8,0x24c425a8,0xa6dda764,0xa41da21f,0xa788a70e,0x2164238b,0xa55fa62f,0xa5eda513,
0xa7fea7d9,0x16481e3e,0xa2d7a472,0xa73ba6a7,0xa7c3a7f6,0x9fc69a46,0x9cb2a0a5,0xa7eaa7a8,
};

#define PROF(slot) do {} while (0)
#define PROF3(slot) do {} while (0)
#define PROF2(slot) do {} while (0)

__device__ __forceinline__ uint32_t smem_u32(const void* p) { return (uint32_t)__cvta_generic_to_shared(p); }

__device__ __forceinline__ void mbar_init(uint32_t a, uint32_t c) {
  asm volatile("mbarrier.init.shared::cta.b64 [%0], %1;\n" ::"r"(a), "r"(c) : "memory");
}
__device__ __forceinline__ void mbar_expect_tx(uint32_t a, uint32_t bytes) {
  asm volatile("mbarrier.arrive.expect_tx.shared::cta.b64 _, [%0], %1;\n" ::"r"(a), "r"(bytes) : "memory");
}
__device__ __forceinline__ void mbar_arrive_cluster(uint32_t cluster_addr) {
  asm volatile("mbarrier.arrive.shared::cluster.b64 _, [%0];\n" ::"r"(cluster_addr) : "memory");
}
__device__ __forceinline__ void mbar_arrive_cluster_n(uint32_t cluster_addr, uint32_t n) {
  asm volatile("mbarrier.arrive.shared::cluster.b64 _, [%0], %1;\n" ::"r"(cluster_addr), "r"(n) : "memory");
}
__device__ __forceinline__ bool mbar_try(uint32_t a, uint32_t parity) {
  uint32_t ok;
  asm volatile("{\n.reg .pred p;\nmbarrier.try_wait.parity.shared::cta.b64 p, [%1], %2;\nselp.u32 %0, 1, 0, p;\n}\n"
               : "=r"(ok) : "r"(a), "r"(parity) : "memory");
  return ok;
}
__device__ __forceinline__ void mbar_wait(uint32_t a, uint32_t parity) {
  if (mbar_try(a, parity)) return;
#pragma unroll 1
  for (int n = 0; n < SPIN_LIMIT; n++)
    if (mbar_try(a, parity)) break;
}
__device__ __forceinline__ bool elect_one() {
  uint32_t p;
  asm volatile("{\n.reg .pred P;\nelect.sync _|P, 0xffffffff;\nselp.u32 %0, 1, 0, P;\n}\n" : "=r"(p));
  return p;
}
__device__ __forceinline__ uint32_t mapa(uint32_t a, uint32_t rank) {
  uint32_t r;
  asm volatile("mapa.shared::cluster.u32 %0, %1, %2;\n" : "=r"(r) : "r"(a), "r"(rank));
  return r;
}
__device__ __forceinline__ void nb_sync(int id, int n) { asm volatile("bar.sync %0, %1;\n" ::"r"(id), "r"(n) : "memory"); }
__device__ __forceinline__ void nb_arrive(int id, int n) { asm volatile("bar.arrive %0, %1;\n" ::"r"(id), "r"(n) : "memory"); }
__device__ __forceinline__ void cluster_sync_all() {
  asm volatile("barrier.cluster.arrive.relaxed.aligned;\nbarrier.cluster.wait.aligned;\n" ::: "memory");
}
__device__ __forceinline__ void fence_async_smem() { asm volatile("fence.proxy.async.shared::cta;\n" ::: "memory"); }
__device__ __forceinline__ void fence_async_all() { asm volatile("fence.proxy.async.global;\n" ::: "memory"); }

__device__ __forceinline__ void tma_load_3d(uint32_t dst, const CUtensorMap* tm, uint32_t bar, int c0, int c1, int c2) {
  asm volatile(
      "cp.async.bulk.tensor.3d.shared::cluster.global.mbarrier::complete_tx::bytes [%0], [%1, {%3, %4, %5}], [%2];\n"
      ::"r"(dst), "l"(tm), "r"(bar), "r"(c0), "r"(c1), "r"(c2) : "memory");
}
__device__ __forceinline__ void tma_load_4d(uint32_t dst, const CUtensorMap* tm, uint32_t bar, int c0, int c1, int c2, int c3) {
  asm volatile(
      "cp.async.bulk.tensor.4d.shared::cluster.global.mbarrier::complete_tx::bytes [%0], [%1, {%3, %4, %5, %6}], [%2];\n"
      ::"r"(dst), "l"(tm), "r"(bar), "r"(c0), "r"(c1), "r"(c2), "r"(c3) : "memory");
}
__device__ __forceinline__ void tma_load_3d_mc(uint32_t dst, const CUtensorMap* tm, uint32_t bar, int c0, int c1, int c2) {
  asm volatile(
      "cp.async.bulk.tensor.3d.shared::cluster.global.mbarrier::complete_tx::bytes.multicast::cluster [%0], [%1, {%3, %4, %5}], [%2], %6;\n"
      ::"r"(dst), "l"(tm), "r"(bar), "r"(c0), "r"(c1), "r"(c2), "h"((uint16_t)3) : "memory");
}
__device__ __forceinline__ void tma_load_5d(uint32_t dst, const CUtensorMap* tm, uint32_t bar, int c0, int c4) {
  asm volatile(
      "cp.async.bulk.tensor.5d.shared::cluster.global.mbarrier::complete_tx::bytes [%0], [%1, {%3, %5, %5, %5, %4}], [%2];\n"
      ::"r"(dst), "l"(tm), "r"(bar), "r"(c0), "r"(c4), "r"(0) : "memory");
}
__device__ __forceinline__ void bulk_load(uint32_t dst, const void* src, uint32_t bytes, uint32_t bar) {
  asm volatile("cp.async.bulk.shared::cluster.global.mbarrier::complete_tx::bytes [%0], [%1], %2, [%3];\n"
               ::"r"(dst), "l"(src), "r"(bytes), "r"(bar) : "memory");
}
__device__ __forceinline__ void bulk_commit() { asm volatile("cp.async.bulk.commit_group;\n" ::: "memory"); }
__device__ __forceinline__ void bulk_wait0() { asm volatile("cp.async.bulk.wait_group 0;\n" ::: "memory"); }
__device__ __forceinline__ void prefetch_tmap(const CUtensorMap* tm) {
  asm volatile("prefetch.tensormap [%0];\n" ::"l"(tm) : "memory");
}

__device__ __forceinline__ void wg_fence() { asm volatile("wgmma.fence.sync.aligned;\n" ::: "memory"); }
__device__ __forceinline__ void wg_commit() { asm volatile("wgmma.commit_group.sync.aligned;\n" ::: "memory"); }
template <int N> __device__ __forceinline__ void wg_wait() {
  asm volatile("wgmma.wait_group.sync.aligned %0;\n" ::"n"(N) : "memory");
}
__device__ __forceinline__ uint64_t mkdesc(uint32_t addr, uint32_t lbo, uint32_t sbo, uint32_t swz) {
  return (uint64_t)((addr & 0x3FFFF) >> 4) | ((uint64_t)(lbo >> 4) << 16) | ((uint64_t)(sbo >> 4) << 32) |
         ((uint64_t)swz << 62);
}

#define R4(d, o) "+f"(d[o + 0]), "+f"(d[o + 1]), "+f"(d[o + 2]), "+f"(d[o + 3])
#define R8(d, o) R4(d, o), R4(d, o + 4)
#define R16(d, o) R8(d, o), R8(d, o + 8)
#define R32(d, o) R16(d, o), R16(d, o + 16)
#define R64(d, o) R32(d, o), R32(d, o + 32)

__device__ __forceinline__ void wgmma_n192(float (&d)[96], uint64_t da, uint64_t db, uint32_t acc) {
  asm volatile(
      "{\n.reg .pred p;\nsetp.ne.u32 p, %98, 0;\n"
      "wgmma.mma_async.sync.aligned.m64n192k16.f32.bf16.bf16 "
      "{%0,%1,%2,%3,%4,%5,%6,%7,%8,%9,%10,%11,%12,%13,%14,%15,%16,%17,%18,%19,%20,%21,%22,%23,%24,%25,%26,%27,%28,%29,%30,%31,"
      "%32,%33,%34,%35,%36,%37,%38,%39,%40,%41,%42,%43,%44,%45,%46,%47,%48,%49,%50,%51,%52,%53,%54,%55,%56,%57,%58,%59,%60,%61,%62,%63,"
      "%64,%65,%66,%67,%68,%69,%70,%71,%72,%73,%74,%75,%76,%77,%78,%79,%80,%81,%82,%83,%84,%85,%86,%87,%88,%89,%90,%91,%92,%93,%94,%95}, "
      "%96, %97, p, 1, 1, 0, 1;\n}\n"
      : R64(d, 0), R32(d, 64)
      : "l"(da), "l"(db), "r"(acc));
}
__device__ __forceinline__ void wgmma_n128(float (&d)[64], uint64_t da, uint64_t db, uint32_t acc) {
  asm volatile(
      "{\n.reg .pred p;\nsetp.ne.u32 p, %66, 0;\n"
      "wgmma.mma_async.sync.aligned.m64n128k16.f32.bf16.bf16 "
      "{%0,%1,%2,%3,%4,%5,%6,%7,%8,%9,%10,%11,%12,%13,%14,%15,%16,%17,%18,%19,%20,%21,%22,%23,%24,%25,%26,%27,%28,%29,%30,%31,"
      "%32,%33,%34,%35,%36,%37,%38,%39,%40,%41,%42,%43,%44,%45,%46,%47,%48,%49,%50,%51,%52,%53,%54,%55,%56,%57,%58,%59,%60,%61,%62,%63}, "
      "%64, %65, p, 1, 1, 0, 1;\n}\n"
      : R64(d, 0)
      : "l"(da), "l"(db), "r"(acc));
}
template <int N> __device__ __forceinline__ void fence_regs(float (&d)[N]) {
#pragma unroll
  for (int i = 0; i < N; i++) asm volatile("" : "+f"(d[i])::"memory");
}

__device__ __forceinline__ void mma16816(float (&d)[4], uint32_t a0, uint32_t a1, uint32_t a2, uint32_t a3, uint32_t b0,
                                         uint32_t b1) {
  asm("mma.sync.aligned.m16n8k16.row.col.f32.bf16.bf16.f32 {%0,%1,%2,%3}, {%4,%5,%6,%7}, {%8,%9}, {%0,%1,%2,%3};\n"
      : "+f"(d[0]), "+f"(d[1]), "+f"(d[2]), "+f"(d[3])
      : "r"(a0), "r"(a1), "r"(a2), "r"(a3), "r"(b0), "r"(b1));
}
__device__ __forceinline__ void mma16816_z(float (&d)[4], uint32_t a0, uint32_t a1, uint32_t a2, uint32_t a3, uint32_t b0,
                                           uint32_t b1) {
  asm("mma.sync.aligned.m16n8k16.row.col.f32.bf16.bf16.f32 {%0,%1,%2,%3}, {%4,%5,%6,%7}, {%8,%9}, {%10,%10,%10,%10};\n"
      : "=f"(d[0]), "=f"(d[1]), "=f"(d[2]), "=f"(d[3])
      : "r"(a0), "r"(a1), "r"(a2), "r"(a3), "r"(b0), "r"(b1), "f"(0.f));
}
__device__ __forceinline__ void ldsm4t(uint32_t (&r)[4], uint32_t a) {
  asm volatile("ldmatrix.sync.aligned.m8n8.x4.trans.shared.b16 {%0,%1,%2,%3}, [%4];\n"
               : "=r"(r[0]), "=r"(r[1]), "=r"(r[2]), "=r"(r[3]) : "r"(a) : "memory");
}
__device__ __forceinline__ void ldsm2t(uint32_t& r0, uint32_t& r1, uint32_t a) {
  asm volatile("ldmatrix.sync.aligned.m8n8.x2.trans.shared.b16 {%0,%1}, [%2];\n" : "=r"(r0), "=r"(r1) : "r"(a) : "memory");
}
__device__ __forceinline__ void st_async128(uint32_t a, uint32_t bar, uint32_t x, uint32_t y, uint32_t z, uint32_t w) {
  asm volatile("st.async.weak.shared::cluster.mbarrier::complete_tx::bytes.v4.b32 [%0], {%2,%3,%4,%5}, [%1];\n"
               ::"r"(a), "r"(bar), "r"(x), "r"(y), "r"(z), "r"(w) : "memory");
}
__device__ __forceinline__ void mbar_arrive(uint32_t a) {
  asm volatile("mbarrier.arrive.shared::cta.b64 _, [%0];\n" ::"r"(a) : "memory");
}
__device__ __forceinline__ void stsm4(uint32_t a, uint32_t r0, uint32_t r1, uint32_t r2, uint32_t r3) {
  asm volatile("stmatrix.sync.aligned.m8n8.x4.shared.b16 [%0], {%1,%2,%3,%4};\n"
               ::"r"(a), "r"(r0), "r"(r1), "r"(r2), "r"(r3) : "memory");
}
__device__ __forceinline__ void stsm4t(uint32_t a, uint32_t r0, uint32_t r1, uint32_t r2, uint32_t r3) {
  asm volatile("stmatrix.sync.aligned.m8n8.x4.trans.shared.b16 [%0], {%1,%2,%3,%4};\n"
               ::"r"(a), "r"(r0), "r"(r1), "r"(r2), "r"(r3) : "memory");
}
__device__ __forceinline__ uint2 lds64(uint32_t a) {
  uint2 v;
  asm volatile("ld.shared.v2.u32 {%0,%1}, [%2];\n" : "=r"(v.x), "=r"(v.y) : "r"(a));
  return v;
}
__device__ __forceinline__ uint4 lds128(uint32_t a) {
  uint4 v;
  asm volatile("ld.shared.v4.u32 {%0,%1,%2,%3}, [%4];\n" : "=r"(v.x), "=r"(v.y), "=r"(v.z), "=r"(v.w) : "r"(a) : "memory");
  return v;
}
__device__ __forceinline__ void sts128(uint32_t a, uint32_t x, uint32_t y, uint32_t z, uint32_t w) {
  asm volatile("st.shared.v4.u32 [%0], {%1,%2,%3,%4};\n" ::"r"(a), "r"(x), "r"(y), "r"(z), "r"(w) : "memory");
}
__device__ __forceinline__ uint32_t pack_bf16(float lo, float hi) {
  uint32_t r;
  asm("cvt.rn.bf16x2.f32 %0, %1, %2;\n" : "=r"(r) : "f"(hi), "f"(lo));
  return r;
}
__device__ __forceinline__ uint32_t bmul2(uint32_t a, uint32_t b) {
  uint32_t r;
  asm("mul.rn.bf16x2 %0, %1, %2;\n" : "=r"(r) : "r"(a), "r"(b));
  return r;
}
__device__ __forceinline__ uint32_t bmax2(uint32_t a, uint32_t b) {
  uint32_t r;
  asm("max.bf16x2 %0, %1, %2;\n" : "=r"(r) : "r"(a), "r"(b));
  return r;
}
__device__ __forceinline__ uint32_t bfma2(uint32_t a, uint32_t b, uint32_t c) {
  uint32_t r;
  asm("fma.rn.bf16x2 %0, %1, %2, %3;\n" : "=r"(r) : "r"(a), "r"(b), "r"(c));
  return r;
}
__device__ __forceinline__ uint32_t badd2(uint32_t a, uint32_t b) {
  uint32_t r;
  asm("add.rn.bf16x2 %0, %1, %2;\n" : "=r"(r) : "r"(a), "r"(b));
  return r;
}
__device__ __forceinline__ void prefetch_l2(const void* p) { asm volatile("prefetch.global.L2 [%0];\n" ::"l"(p)); }
__device__ __forceinline__ void cp_async16n(uint32_t dst, const void* src) {
  asm volatile("cp.async.cg.shared.global [%0], [%1], 16;\n" ::"r"(dst), "l"(src) : "memory");
}
__device__ __forceinline__ void cp_async16(uint32_t dst, const void* src, uint32_t srcbytes) {
  asm volatile("cp.async.cg.shared.global.L2::256B [%0], [%1], 16, %2;\n" ::"r"(dst), "l"(src), "r"(srcbytes) : "memory");
}
__device__ __forceinline__ uint32_t ld_acquire(const uint32_t* p) {
  uint32_t v;
  asm volatile("ld.acquire.gpu.global.u32 %0, [%1];\n" : "=r"(v) : "l"(p) : "memory");
  return v;
}
__device__ __forceinline__ uint32_t ld_relaxed(const uint32_t* p) {
  uint32_t v;
  asm volatile("ld.relaxed.gpu.global.u32 %0, [%1];\n" : "=r"(v) : "l"(p) : "memory");
  return v;
}
__device__ __forceinline__ void st_release(uint32_t* p, uint32_t v) {
  asm volatile("st.release.gpu.global.u32 [%0], %1;\n" ::"l"(p), "r"(v) : "memory");
}
__device__ __forceinline__ void wait_flag(const uint32_t* p, uint32_t want) {
  int n = 0;
  while (ld_relaxed(p) != want && ++n < SPIN_LIMIT) __nanosleep(40);
  (void)ld_acquire(p);
}

struct Params {
  const __nv_bfloat16* x;
  const __nv_bfloat16* w;
  const __nv_bfloat16* q;
  const __nv_bfloat16* k;
  const __nv_bfloat16* v;
  const __nv_bfloat16* shift_k;
  const __nv_bfloat16* ssm_k;
  const __nv_bfloat16* ssm_D;
  const __nv_bfloat16* wo;
  __nv_bfloat16* out;
};

__device__ __forceinline__ uint32_t lds32(uint32_t a) {
  uint32_t v;
  asm volatile("ld.shared.u32 %0, [%1];\n" : "=r"(v) : "r"(a));
  return v;
}
#define W4(d, o) "=f"(d[o + 0]), "=f"(d[o + 1]), "=f"(d[o + 2]), "=f"(d[o + 3])
#define W8(d, o) W4(d, o), W4(d, o + 4)
#define W16(d, o) W8(d, o), W8(d, o + 8)
#define U4(c, d, o) c(d[o + 0]), c(d[o + 1]), c(d[o + 2]), c(d[o + 3])
#define U8(c, d, o) U4(c, d, o), U4(c, d, o + 4)
#define U16(c, d, o) U8(c, d, o), U8(c, d, o + 8)
#define U32(c, d, o) U16(c, d, o), U16(c, d, o + 16)
#define D32 "{%0,%1,%2,%3,%4,%5,%6,%7,%8,%9,%10,%11,%12,%13,%14,%15,%16,%17,%18,%19,%20,%21,%22,%23,%24,%25,%26,%27,%28,%29,%30,%31}"
#define D16 "{%0,%1,%2,%3,%4,%5,%6,%7,%8,%9,%10,%11,%12,%13,%14,%15}"
#define D8 "{%0,%1,%2,%3,%4,%5,%6,%7}"
template <int ACC> __device__ __forceinline__ void hmma_n128t(uint32_t (&d)[32], const uint32_t (&a)[4], uint64_t db) {
  if (ACC)
    asm volatile("wgmma.mma_async.sync.aligned.m64n128k16.f16.f16.f16 " D32 ", {%32,%33,%34,%35}, %36, 1, 1, 1, 1;\n"
                 : U32("+r", d, 0) : "r"(a[0]), "r"(a[1]), "r"(a[2]), "r"(a[3]), "l"(db));
  else
    asm volatile("wgmma.mma_async.sync.aligned.m64n128k16.f16.f16.f16 " D32 ", {%32,%33,%34,%35}, %36, 0, 1, 1, 1;\n"
                 : U32("=r", d, 0) : "r"(a[0]), "r"(a[1]), "r"(a[2]), "r"(a[3]), "l"(db));
}
template <int ACC, int TB> __device__ __forceinline__ void hmma_n32(uint32_t (&d)[8], const uint32_t (&a)[4], uint64_t db) {
  if (ACC)
    asm volatile("wgmma.mma_async.sync.aligned.m64n32k16.f16.f16.f16 " D8 ", {%8,%9,%10,%11}, %12, 1, 1, 1, %13;\n"
                 : U8("+r", d, 0) : "r"(a[0]), "r"(a[1]), "r"(a[2]), "r"(a[3]), "l"(db), "n"(TB));
  else
    asm volatile("wgmma.mma_async.sync.aligned.m64n32k16.f16.f16.f16 " D8 ", {%8,%9,%10,%11}, %12, 0, 1, 1, %13;\n"
                 : U8("=r", d, 0) : "r"(a[0]), "r"(a[1]), "r"(a[2]), "r"(a[3]), "l"(db), "n"(TB));
}
template <int ACC> __device__ __forceinline__ void fmma_n32t(float (&d)[16], const uint32_t (&a)[4], uint64_t db) {
  if (ACC)
    asm volatile("wgmma.mma_async.sync.aligned.m64n32k16.f32.f16.f16 " D16 ", {%16,%17,%18,%19}, %20, 1, 1, 1, 1;\n"
                 : R16(d, 0) : "r"(a[0]), "r"(a[1]), "r"(a[2]), "r"(a[3]), "l"(db));
  else
    asm volatile("wgmma.mma_async.sync.aligned.m64n32k16.f32.f16.f16 " D16 ", {%16,%17,%18,%19}, %20, 0, 1, 1, 1;\n"
                 : W16(d, 0) : "r"(a[0]), "r"(a[1]), "r"(a[2]), "r"(a[3]), "l"(db));
}
template <int N> __device__ __forceinline__ void fence_regs(uint32_t (&d)[N]) {
#pragma unroll
  for (int i = 0; i < N; i++) asm volatile("" : "+r"(d[i])::"memory");
}
__device__ __forceinline__ uint32_t hmul(uint32_t a, uint32_t b) { uint32_t r; asm("mul.rn.f16x2 %0, %1, %2;\n" : "=r"(r) : "r"(a), "r"(b)); return r; }
__device__ __forceinline__ uint32_t hadd(uint32_t a, uint32_t b) { uint32_t r; asm("add.rn.f16x2 %0, %1, %2;\n" : "=r"(r) : "r"(a), "r"(b)); return r; }
__device__ __forceinline__ uint32_t hsub(uint32_t a, uint32_t b) { uint32_t r; asm("sub.rn.f16x2 %0, %1, %2;\n" : "=r"(r) : "r"(a), "r"(b)); return r; }
__device__ __forceinline__ uint32_t hfma(uint32_t a, uint32_t b, uint32_t c) { uint32_t r; asm("fma.rn.f16x2 %0, %1, %2, %3;\n" : "=r"(r) : "r"(a), "r"(b), "r"(c)); return r; }
__device__ __forceinline__ uint32_t hfnma(uint32_t a, uint32_t b, uint32_t c) {
  uint32_t r;
  asm("{\n.reg .b32 t;\nneg.f16x2 t, %1;\nfma.rn.f16x2 %0, t, %2, %3;\n}\n" : "=r"(r) : "r"(a), "r"(b), "r"(c));
  return r;
}
__device__ __forceinline__ uint32_t hrefl(uint32_t p, uint32_t s) {
  uint32_t r;
  asm("{\n.reg .b32 t;\nneg.f16x2 t, %2;\nfma.rn.f16x2 %0, %1, %3, t;\n}\n" : "=r"(r) : "r"(p), "r"(s), "r"(0x40004000u));
  return r;
}
__device__ __forceinline__ void bfly(uint32_t xr, uint32_t xi, uint32_t tr, uint32_t ti, uint32_t yr, uint32_t yi, uint32_t ur,
                                     uint32_t ui, uint32_t& sr, uint32_t& si, uint32_t& dr, uint32_t& di) {
  const uint32_t pr = hfnma(xi, ti, hmul(xr, tr)), pi = hfma(xi, tr, hmul(xr, ti));
  sr = hfnma(yi, ui, hfma(yr, ur, pr));
  si = hfma(yi, ur, hfma(yr, ui, pi));
  dr = hrefl(pr, sr);
  di = hrefl(pi, si);
}
template <int BH> __device__ __forceinline__ void fft_e1(const uint32_t (&d)[32], const uint32_t (&tw)[16], uint32_t (&a2)[2][2][4]) {
#pragma unroll
  for (int be = 0; be < 2; be++)
#pragma unroll
    for (int s = 0; s < 2; s++) {
      const int o = 16 * s + 8 * be + 2 * BH, p = 2 * BH;
      bfly(d[o], d[o + 1], tw[p], tw[p + 1], d[o + 4], d[o + 5], tw[p + 4], tw[p + 5], a2[be][0][s], a2[be][0][2 + s],
           a2[be][1][s], a2[be][1][2 + s]);
    }
}
__device__ __forceinline__ uint32_t hfms(uint32_t a, uint32_t b, uint32_t c) {
  uint32_t r;
  asm("{\n.reg .b32 t;\nneg.f16x2 t, %3;\nfma.rn.f16x2 %0, %1, %2, t;\n}\n" : "=r"(r) : "r"(a), "r"(b), "r"(c));
  return r;
}
template <int C, int J> __device__ __forceinline__ void fft_e2(const uint32_t (&d0)[8], const uint32_t (&d1)[8], uint32_t (&a3)[2][4]) {
  const uint32_t ur = d0[2 * J], ui = d0[4 + 2 * J], hr = d0[2 * J + 1], hi = d0[5 + 2 * J];
  const uint32_t vr = d1[2 * J], vi = d1[4 + 2 * J], gr = d1[2 * J + 1], gi = d1[5 + 2 * J];
  const uint32_t pr = hfnma(ui, hi, hmul(ur, hr)), pi = hfma(ui, hr, hmul(ur, hi));
  a3[0][2 + C] = pr;
  a3[0][C] = pi;
  a3[1][2 + C] = hfnma(vi, hi, hfma(vr, hr, hfnma(ui, gi, hfms(ur, gr, pi))));
  a3[1][C] = hfma(vi, hr, hfma(vr, hi, hfma(ui, gr, hfma(ur, gi, pr))));
}
__device__ __forceinline__ void fft_e3(const uint32_t (&d)[2][8], const uint32_t (&tw)[16], uint32_t zaddr) {
#pragma unroll
  for (int rho = 0; rho < 2; rho++) {
    uint32_t zr[4], zi[4];
#pragma unroll
    for (int nb = 0; nb < 4; nb++) {
      const uint32_t xi = d[nb >> 1][2 * (nb & 1) + rho], xr = d[nb >> 1][4 + 2 * (nb & 1) + rho];
      const uint32_t tr = tw[8 + 4 * rho + 2 * (nb & 1)], ti = tw[9 + 4 * rho + 2 * (nb & 1)];
      zr[nb] = hfnma(xi, ti, hmul(xr, tr));
      zi[nb] = hfma(xi, tr, hmul(xr, ti));
    }
    stsm4(zaddr + rho * 1024, zr[0], zr[1], zr[2], zr[3]);
    stsm4(zaddr + rho * 1024 + 512, zi[0], zi[1], zi[2], zi[3]);
  }
}
__device__ __forceinline__ float bf_lo(uint32_t v) {
  uint32_t r;
  asm("prmt.b32 %0, %1, 0, 0x1044;\n" : "=r"(r) : "r"(v));
  return __uint_as_float(r);
}
__device__ __forceinline__ float bf_hi(uint32_t v) { return __uint_as_float(v & 0xffff0000u); }
__device__ __forceinline__ float ex2(float x) {
  float r;
  asm("ex2.approx.ftz.f32 %0, %1;\n" : "=f"(r) : "f"(x));
  return r;
}
__device__ __forceinline__ float rcp(float x) {
  float r;
  asm("rcp.approx.ftz.f32 %0, %1;\n" : "=f"(r) : "f"(x));
  return r;
}

__device__ __forceinline__ int g2_a(int s) { return ((0xA1054 >> (4 * s)) & 15) * 16384; }
__device__ __forceinline__ int g2_b(int s) { return ((0xCDB32 >> (4 * s)) & 15) * 16384; }
static_assert(OFF_U == 10 * 16384 && OFF_H == 12 * 16384 && OFF_OP == 4 * 16384, "units");
__device__ __forceinline__ int g2_k(int hp, int i) { return i < 2 ? hp ^ 1 ^ i : i < 4 ? (hp & ~1) ^ i : ((hp & ~3) + i) & 15; }
__device__ __forceinline__ int y_slot(int wg, int it) {
  static_assert(T_B2 == T_TW + 8192 && T_A1 == T_B2 + 4096, "y slots");
  return OFF_T + T_TW + ((it + 3) & 3) * 4096 + wg * 2048;
}

__device__ __forceinline__ void to_arr(uint32_t (&d)[4], uint4 v) { d[0] = v.x; d[1] = v.y; d[2] = v.z; d[3] = v.w; }

__device__ __forceinline__ void attn_stage(uint32_t sb, int blk, int lane, const float (&acc)[96], uint32_t (&k1)[2][4]) {
  const int lr = lane & 7, lm = lane >> 3;
  const uint32_t base = sb + OFF_VP + (blk * 16 + lr + 8 * (lm & 1)) * 128;
#pragma unroll
  for (int i = 0; i < 8; i++) k1[i >> 2][i & 3] = pack_bf16(acc[34 + 4 * i], acc[35 + 4 * i]);
  const uint32_t kh = sb + OFF_KH + blk * 2048 + lane * 16;
  sts128(kh, k1[0][0], k1[0][1], k1[0][2], k1[0][3]);
  sts128(kh + 512, k1[1][0], k1[1][1], k1[1][2], k1[1][3]);
#pragma unroll
  for (int j = 0; j < 8; j += 2)
    stsm4(base + (((j + (lm >> 1)) ^ lr) << 4), pack_bf16(acc[64 + 4 * j], acc[65 + 4 * j]),
          pack_bf16(acc[66 + 4 * j], acc[67 + 4 * j]), pack_bf16(acc[68 + 4 * j], acc[69 + 4 * j]),
          pack_bf16(acc[70 + 4 * j], acc[71 + 4 * j]));
}
__device__ __forceinline__ void attn_pack(const float (&acc)[96], uint32_t (&qa)[2][8], uint32_t (&k0)[2][4]) {
#pragma unroll
  for (int hd = 0; hd < 2; hd++) {
#pragma unroll
    for (int i = 0; i < 8; i++) {
      asm volatile("cvt.rn.bf16x2.f32 %0, %1, %2;\n" : "=r"(qa[hd][i]) : "f"(acc[16 * hd + 2 * i + 1]), "f"(acc[16 * hd + 2 * i]));
    }
#pragma unroll
    for (int i = 0; i < 4; i++) {
      asm volatile("cvt.rn.bf16x2.f32 %0, %1, %2;\n" : "=r"(k0[hd][i]) : "f"(acc[33 + 16 * hd + 4 * i]), "f"(acc[32 + 16 * hd + 4 * i]));
    }
  }
}
__device__ __forceinline__ void attn_own(const uint32_t (&k0)[2][4], const uint32_t (&k1)[2][4], bool le0, bool le1,
                                         const uint32_t (&qa)[2][8], float (&l)[2][4]) {
#pragma unroll
  for (int hd = 0; hd < 2; hd++) {
    float s0[4], s1[4];
    mma16816_z(s0, qa[hd][0], qa[hd][1], qa[hd][2], qa[hd][3], k0[hd][0], k0[hd][1]);
    mma16816_z(s1, qa[hd][0], qa[hd][1], qa[hd][2], qa[hd][3], k1[hd][0], k1[hd][1]);
    mma16816(s0, qa[hd][4], qa[hd][5], qa[hd][6], qa[hd][7], k0[hd][2], k0[hd][3]);
    mma16816(s1, qa[hd][4], qa[hd][5], qa[hd][6], qa[hd][7], k1[hd][2], k1[hd][3]);
    l[hd][0] = s0[0];
    l[hd][1] = s0[1];
    l[hd][2] = le0 ? s1[2] : s0[2];
    l[hd][3] = le1 ? s1[3] : s0[3];
  }
}
template <int N> __device__ __forceinline__ void quad_softmax(float (&x)[N][2], uint32_t (&pp)[N]) {
  const float c2 = 1.4426950408889634f;
  uint32_t q[N], mx[N / 2];
#pragma unroll
  for (int n = 0; n < N; n++) {
    const uint32_t r = pack_bf16(x[n][0], x[n][1]);
    q[n] = bfma2(r, 0x3e353e35u, bmul2(r, 0x379e379eu));
    x[n][0] = bf_lo(q[n]);
    x[n][1] = bf_hi(q[n]);
  }
#pragma unroll
  for (int n = 0; n < N / 2; n++)
    mx[n] = bmax2(__byte_perm(q[2 * n], q[2 * n + 1], 0x5410), __byte_perm(q[2 * n], q[2 * n + 1], 0x7632));
#pragma unroll
  for (int o = 1; o <= 2; o++)
#pragma unroll
    for (int n = 0; n < N / 2; n++) mx[n] = bmax2(mx[n], __shfl_xor_sync(0xffffffffu, mx[n], o));
  float m[N], t[N];
#pragma unroll
  for (int n = 0; n < N / 2; n++) {
    m[2 * n] = bf_lo(mx[n]);
    m[2 * n + 1] = bf_hi(mx[n]);
  }
#pragma unroll
  for (int n = 0; n < N; n++) {
    const float nm = -m[n] * c2;
    x[n][0] = ex2(fmaf(x[n][0], c2, nm));
    x[n][1] = ex2(fmaf(x[n][1], c2, nm));
    t[n] = x[n][0] + x[n][1];
  }
#pragma unroll
  for (int o = 1; o <= 2; o++)
#pragma unroll
    for (int n = 0; n < N; n++) t[n] += __shfl_xor_sync(0xffffffffu, t[n], o);
#pragma unroll
  for (int n = 0; n < N; n++) {
    const float inv = rcp(t[n]);
    pp[n] = pack_bf16(x[n][0] * inv, x[n][1] * inv);
  }
}
__device__ __forceinline__ void attn_pv(uint32_t dst, const uint32_t (&va)[4], const uint32_t (&vb)[4], uint32_t pp,
                                        uint32_t maskLE) {
  const uint32_t b0 = pp & ~maskLE, b1 = pp & maskLE;
  float oa[4], ob[4];
  mma16816_z(oa, va[0], va[1], va[2], va[3], b0, b1);
  mma16816_z(ob, vb[0], vb[1], vb[2], vb[3], b0, b1);
  stsm4t(dst, pack_bf16(oa[0], oa[1]), pack_bf16(oa[2], oa[3]), pack_bf16(ob[0], ob[1]), pack_bf16(ob[2], ob[3]));
}

template <int MODE>
__global__ void __cluster_dims__(2, 1, 1) __launch_bounds__(NTHREADS, 1)
fused_kernel(const Params p, const __grid_constant__ CUtensorMap tmX, const __grid_constant__ CUtensorMap tmW,
             const __grid_constant__ CUtensorMap tmWo,
             const __grid_constant__ CUtensorMap tmQ,
             const __grid_constant__ CUtensorMap tmXh, const __grid_constant__ CUtensorMap tmWh) {
  extern __shared__ __align__(1024) uint8_t smem[];
  const uint32_t sb = smem_u32(smem);
  const uint32_t bars = sb + OFF_BAR;
  const int tid = threadIdx.x, lane = tid & 31, warp = __shfl_sync(0xffffffffu, tid >> 5, 0);
  const int rank = blockIdx.x & 1;
  const bool halo_cta = blockIdx.x < 4;
  if (halo_cta && MODE != 0) return;
  int grp, mem;
  {
    const int t = (blockIdx.x >> 1) - 4, u = t - 32;
    const int q7 = (u * 37) >> 8;
    const bool lo = (unsigned)t < 32u, mid = (unsigned)u < 28u;
    grp = lo ? (t & 7) : (mid ? 1 + u - 7 * q7 : 0);
    mem = lo ? (t >> 3) : (mid ? 4 + q7 : (t < 0 ? t + 6 : t - 54));
  }
  const int rg = (grp >> 2) * 4 + (mem >> 1), hp = (grp & 3) * 4 + (mem & 1) * 2 + rank;
  const int rb2 = (grp >> 2) * 8 + mem, cb2 = (grp & 3) * 2 + rank;
  const int chb = grp * 16 + mem * 2 + rank;
  const int cta = rg * 16 + hp;
  const int par = rg >> 2, gidx = rg & 3;

  if (tid < 256 && !halo_cta && MODE != 2) {
    const int r = tid >> 3, c = tid & 7;
    const uint32_t so = r * 128 + ((c ^ (r & 7)) << 4);
    const __nv_bfloat16* wg0 = p.w + (size_t)r * (3 * DM) + hp * 64 + c * 8;
    const __nv_bfloat16* xg0 = p.x + (size_t)(2 * (gidx * 256 + r) + par) * DM + c * 8;
#pragma unroll
    for (int j = 0; j < 3; j++) cp_async16n(sb + OFF_1B + j * 4096 + so, wg0 + j * DM);
#pragma unroll
    for (int i = 0; i < 8; i++) cp_async16n(sb + i * 4096 + so, xg0 + (size_t)i * 64 * DM);
    asm volatile("cp.async.commit_group;\n" ::: "memory");
  }
  if (tid == 256) {
    prefetch_tmap(halo_cta ? &tmXh : &tmX);
#pragma unroll
    for (int i = 0; i < NS1B; i++) mbar_init(bars + 8 * (BAR_FULLB + i), 1);
#pragma unroll
    for (int i = 0; i < NS1A; i++) mbar_init(bars + 8 * (BAR_FULLA + i), 1);
    asm volatile("fence.mbarrier_init.release.cluster;\n" ::: "memory");
    if (!halo_cta && MODE != 2) {
      mbar_expect_tx(bars + 8 * (BAR_FULLB + 1), STG1B);
      tma_load_3d(sb + OFF_1B + 1 * STG1B, &tmW, bars + 8 * (BAR_FULLB + 1), hp * 64, 32, 0);
      mbar_expect_tx(bars + 8 * (BAR_FULLB + 2), STG1B);
      tma_load_3d(sb + OFF_1B + 2 * STG1B, &tmW, bars + 8 * (BAR_FULLB + 2), hp * 64, 64, 0);
    } else {
      prefetch_tmap(&tmWh);
    }
  } else if (tid == 288) {
#pragma unroll
    for (int i = 0; i < NS1A; i++) mbar_init(bars + 8 * (BAR_EMPTYA + i), 4);
#pragma unroll
    for (int i = 0; i < NS1B; i++) mbar_init(bars + 8 * (BAR_EMPTYB + i), 2);
    asm volatile("fence.mbarrier_init.release.cluster;\n" ::: "memory");
  } else if (tid == 320) {
#pragma unroll
    for (int i = 0; i < NS2; i++) {
      mbar_init(bars + 8 * (BAR_FULL2 + i), 1);
      mbar_init(bars + 8 * (BAR_EMPTY2 + i), 4);
    }
    mbar_init(bars + 8 * BAR_DEAD, 2);
    mbar_init(bars + 8 * (BAR_DEAD + 1), 2);
    mbar_init(bars + 8 * BAR_X, 2);
    mbar_init(bars + 8 * BAR_REL, 2);
    asm volatile("fence.mbarrier_init.release.cluster;\n" ::: "memory");
  } else if (tid == 352) {
    mbar_init(bars + 8 * BAR_T, 1);
    mbar_init(bars + 8 * BAR_UH, 3);
    mbar_init(bars + 8 * BAR_LFREE, 4);
    mbar_init(bars + 8 * BAR_LAND, 1);
    mbar_init(bars + 8 * BAR_U, 1);
    mbar_init(bars + 8 * BAR_Q, 1);
    mbar_init(bars + 8 * BAR_STG, 9);
    asm volatile("fence.mbarrier_init.release.cluster;\n" ::: "memory");
  }
  if (warp == 8) PROF2(23);
  cluster_sync_all();
  if (warp == 8) PROF2(24);

  if (warp >= 8) {
    const int hw = warp - 8;
    const int lr = lane & 7, lm = lane >> 3;
    auto g1_issue_a = [&](int j, int s) {
      const uint32_t fb = bars + 8 * (BAR_FULLA + s);
      mbar_expect_tx(fb, STG1A);
      tma_load_3d_mc(sb + s * STG1A + rank * 16384, &tmX, fb, j * 64, par, gidx * 256 + rank * 128);
    };
    auto g1_issue_b = [&](int kb, int s) {
      const uint32_t fb = bars + 8 * (BAR_FULLB + s);
      mbar_expect_tx(fb, STG1B);
      tma_load_3d(sb + OFF_1B + s * STG1B, &tmW, fb, hp * 64, kb * 32, 0);
    };
    asm volatile("setmaxnreg.dec.sync.aligned.u32 %0;\n" :: "n"(REG_HELP));

    if (halo_cta) {
      if (hw == 0) {
        int s = 0, ph = 1;
#pragma unroll 1
        for (int kb = 0; kb < 16; kb++) {
          mbar_wait(bars + 8 * (BAR_EMPTYB + s), ph);
          const uint32_t fb = bars + 8 * (BAR_FULLB + s), st = sb + s * STGH;
          if (elect_one()) {
            mbar_expect_tx(fb, STGH);
            tma_load_4d(st, &tmXh, fb, kb * 64, 248, 0, 0);
            tma_load_3d(st + 8192, &tmWh, fb, 0, kb * 64, 16 + blockIdx.x * 4);
            tma_load_3d(st + 8192 + 32768, &tmWh, fb, 0, kb * 64, 32 + blockIdx.x * 4);
          }
          if (++s == 3) { s = 0; ph ^= 1; }
        }
      }
      __syncwarp();
    } else if (hw == 0) {
      uint32_t epoch = 0;
      if (lane < (MODE == 2 ? NS2 : 2)) mbar_arrive_cluster_n(mapa(bars, rank) + 8 * (BAR_EMPTY2 + lane), 4);
      if (MODE != 2) {
      epoch = ld_relaxed(g_flag_o + 2 * cta) + 1;
      if (lane == 0) {
        mbar_expect_tx(bars + 8 * BAR_U, 32768);
        mbar_expect_tx(bars + 8 * BAR_LAND, 32768);
        mbar_expect_tx(bars + 8 * BAR_Q, 32768);
        mbar_expect_tx(bars + 8 * BAR_T, T_END);
      }
      {
        int sa = 1, pha = 1, sbb = 2, phb = 1;
#pragma unroll 1
        for (int kb = 2; kb < 32; kb++) {
          if (!(kb & 1)) {
            mbar_wait(bars + 8 * (BAR_EMPTYA + sa), pha);
            if (elect_one()) g1_issue_a(kb >> 1, sa);
            if (++sa == NS1A) { sa = 0; pha ^= 1; }
          }
          mbar_wait(bars + 8 * (BAR_EMPTYB + sbb), phb);
          if (kb > 2 && elect_one()) g1_issue_b(kb, sbb);
          __syncwarp();
          if (kb >= PF0 && kb < PF0 + 12)
            prefetch_l2((kb < PF0 + 8 ? p.q + (size_t)chb * 16384 + (kb - PF0) * 2048 : p.wo + (size_t)chb * 8192 + (kb - PF0 - 8) * 2048) + lane * 64);
          if (kb == 4) PROF2(27);
          if (kb == 1) PROF2(38);
          if (kb == 2) PROF2(39);
          if (++sbb == NS1B) { sbb = 0; phb ^= 1; }
        }
      }
      static_assert(32 % NS1B == 2 && (32 / NS1B) % 2 == 0 && OFF_Q == OFF_1B && 2 * STG1B == 6 * 4096, "slots / parity of these loads");
      const uint8_t* tab = reinterpret_cast<const uint8_t*>(g_tab);
      if (lane == 0) {
        prefetch_tmap(&tmWo);
        prefetch_tmap(&tmQ);
        bulk_load(sb + OFF_T + T_A1, tab + T_A1, T_END - T_A1, bars + 8 * BAR_T);
        mbar_wait(bars + 8 * (BAR_EMPTYB + 2), 1);
        tma_load_5d(sb + OFF_Q + 6 * 4096, &tmQ, bars + 8 * BAR_Q, (chb & ~1) * 8, rank * 32 + 24);
        tma_load_5d(sb + OFF_Q + 7 * 4096, &tmQ, bars + 8 * BAR_Q, (chb & ~1) * 8, rank * 32 + 28);
        if (gidx != 0) wait_flag(g_flag_h + (hp >> 2), epoch);
      }
      __syncwarp();
      {
        uint4 hk0 = make_uint4(0, 0, 0, 0), hk1 = hk0, hv0 = hk0, hv1 = hk0;
        if (gidx != 0) {
          const uint4* src = g_halo + cta * 128 + lane;
          hk0 = __ldcg(src); hk1 = __ldcg(src + 32); hv0 = __ldcg(src + 64); hv1 = __ldcg(src + 96);
        }
        if (lane == 0) {
          mbar_wait(bars + 8 * (BAR_EMPTYB + 3), 1);
          bulk_load(sb + OFF_T, tab, T_TW, bars + 8 * BAR_T);
        }
        __syncwarp();
        PROF2(18);
        sts128(sb + OFF_L0 + 1024 + lane * 16, hk0.x, hk0.y, hk0.z, hk0.w);
        sts128(sb + OFF_L0 + 1536 + lane * 16, hk1.x, hk1.y, hk1.z, hk1.w);
        stsm4(sb + OFF_L0 + lr * 128 + ((lm ^ lr) << 4), hv0.x, hv0.y, hv0.z, hv0.w);
        stsm4(sb + OFF_L0 + lr * 128 + (((4 + lm) ^ lr) << 4), hv1.x, hv1.y, hv1.z, hv1.w);
        __syncwarp();
        if (lane == 0) {
          mbar_arrive(bars + 8 * BAR_STG);
          mbar_wait(bars + 8 * (BAR_EMPTYB + 4), 1);
          bulk_load(sb + OFF_T + T_TW, tab + T_TW, T_A1 - T_TW, bars + 8 * BAR_T);
          mbar_wait(bars + 8 * BAR_EMPTYB, 0);
#pragma unroll 1
          for (int i = 0; i < 6; i++) tma_load_5d(sb + OFF_Q + i * 4096, &tmQ, bars + 8 * BAR_Q, (chb & ~1) * 8, rank * 32 + i * 4);
        }
        __syncwarp();
      }
      }
      if (MODE != 1) {
        auto korder = [&](int i) { return MODE == 2 ? i : g2_k(hp, i); };
        if (MODE == 0) {
          mbar_wait(bars + 8 * (BAR_EMPTY2 + 2), 0);
          if (elect_one()) {
            mbar_expect_tx(bars + 8 * BAR_FULL2, STG2);
            tma_load_3d(sb + g2_b(0), &tmWo, bars + 8 * BAR_FULL2, 0, korder(0) * 64, cb2 * 2);
            tma_load_3d(sb + g2_b(1), &tmWo, bars + 8 * (BAR_FULL2 + 1), 0, korder(1) * 64, cb2 * 2);
          }
        }
        PROF2(20);
        const __nv_bfloat16* osrc = g_o + (size_t)(rb2 >> 1) * 16 * 16384 + ((rb2 & 1) * 2 + rank) * 4096;
        const uint32_t* flag = g_flag_o + (rb2 >> 1) * 32 + korder(lane & 15) * 2 + (rb2 & 1);
        uint32_t ready = MODE == 0 ? 0u : ~0u;
#pragma unroll
        for (int i = MODE == 0 ? 2 : 0; i < 16; i++) {
          const int kb = korder(i), s = i % NS2, ph = (i / NS2) & 1;
          const uint32_t fb = bars + 8 * (BAR_FULL2 + s);
          if (!((ready >> i) & 1)) {
            int n = 0;
            do {
              ready |= __ballot_sync(0xffffffffu, ld_acquire(flag) == epoch);
            } while (!((ready >> i) & 1) && ++n < SPIN_LIMIT);
            fence_async_all();
          }
          if (i == 2) PROF(21);
          mbar_wait(bars + 8 * (BAR_EMPTY2 + s), ph);
          if (elect_one()) {
            mbar_expect_tx(fb, STG2);
            asm volatile(
                "cp.async.bulk.shared::cluster.global.mbarrier::complete_tx::bytes.multicast::cluster [%0], [%1], %2, [%3], %4;\n"
                ::"r"(sb + g2_a(s) + rank * 8192), "l"(osrc + kb * 16384), "r"(8192), "r"(fb), "h"((uint16_t)3) : "memory");
            if (MODE != 0 || i >= 4) tma_load_3d(sb + g2_b(s), &tmWo, fb, 0, kb * 64, cb2 * 2);
          }
          if (i == 3) PROF(37);

        }
      }
      __syncwarp();
    } else if (MODE != 2) {
      {
        const int g = lane >> 2, t = lane & 3;
        uint32_t w[2][4];
#pragma unroll
        for (int h = 0; h < 2; h++) {
          const uint2 x = __ldg(reinterpret_cast<const uint2*>(p.shift_k + ((chb & ~1) * 8 + h * 8 + g) * 4));
          w[h][0] = __byte_perm(x.x, x.x, 0x1010);
          w[h][1] = __byte_perm(x.x, x.x, 0x3232);
          w[h][2] = __byte_perm(x.y, x.y, 0x1010);
          w[h][3] = __byte_perm(x.y, x.y, 0x3232);
        }
        auto swz = [](int r) { return (((r & 29) | ((r ^ (r >> 2)) & 2)) << 5) | (r & 16); };
        const uint32_t kring = sb + OFF_H + (hw - 1) * 8192, vring = kring + 4096;
        const int s0 = rank * 32 + (hw - 1) * 11, s1 = hw == 3 ? rank * 32 + 32 : s0 + 11;
        const size_t goff = (size_t)(lane >> 1) * DM + (chb & ~1) * 8 + (lane & 1) * 8;
        const __nv_bfloat16* kg = p.k + goff;
        const __nv_bfloat16* vg = p.v + goff;
        const uint32_t d0 = swz(lane >> 1) ^ ((lane & 1) << 4), d1 = swz(16 + (lane >> 1)) ^ ((lane & 1) << 4);
        auto issue = [&](int st) {
          const uint32_t so = (st & 3) << 10;
          cp_async16(kring + so + d0, kg + (size_t)st * 32 * DM, 16);
          cp_async16(kring + so + d1, kg + (size_t)(st * 32 + 16) * DM, 16);
          cp_async16(vring + so + d0, vg + (size_t)st * 32 * DM, 16);
          cp_async16(vring + so + d1, vg + (size_t)(st * 32 + 16) * DM, 16);
        };
        const int xa = 8 * (lr >> 1) + 2 * lm + (lr & 1), xb = 8 * (lr >> 1) - 4 + 2 * (lm & 1) + (lr & 1);
        const uint32_t la = swz(xa), lb = swz(xb & 31);
        const int backb = xb < 0 ? 1 : 0;
        const uint32_t ud[2] = {mapa(sb + OFF_U + g * 4096 + t * 16, 0), mapa(sb + OFF_U + g * 4096 + t * 16, 1)};
        const uint32_t ub[2] = {mapa(bars + 8 * BAR_U, 0), mapa(bars + 8 * BAR_U, 1)};
        if (lane == 0) mbar_wait(bars + 8 * (BAR_FULLB + NS1B - 1), 0);
        __syncwarp();
        if (lane >= 24) cp_async16(kring + (((s0 - 1) & 3) << 10) + d1, s0 > 0 ? kg + (size_t)(s0 * 32 - 16) * DM : kg, s0 > 0 ? 16 : 0);
        issue(s0);
        asm volatile("cp.async.commit_group;\n" ::: "memory");
        issue(s0 + 1);
        asm volatile("cp.async.commit_group;\n" ::: "memory");
#pragma unroll 1
        for (int st = s0; st < s1; st++) {
          if (st + 2 < s1) issue(st + 2);
          if (hw == 1 && st - s0 < 8) prefetch_l2(p.ssm_k + (size_t)(chb * 8 + st - s0) * SEQ + lane * 64);
          if (hw == 2 && st == s0 + 4 && lane < 2) prefetch_l2(g_tab + (chb * 2 + lane) * 32);
          const uint32_t uo = (st ^ ((g ^ (st >> 2)) & 1)) * 64;
          asm volatile("cp.async.commit_group;\n" ::: "memory");
          asm volatile("cp.async.wait_group 2;\n" ::: "memory");
          __syncwarp();
#pragma unroll
          for (int h = 0; h < 2; h++) {
            uint32_t e[6], vv[4], e4[4];
            ldsm4t(e4, kring + ((st & 3) << 10) + (la ^ (h << 4)));
            ldsm2t(e[0], e[1], kring + (((st - backb) & 3) << 10) + (lb ^ (h << 4)));
            ldsm4t(vv, vring + ((st & 3) << 10) + (la ^ (h << 4)));
            e[2] = e4[0]; e[3] = e4[1]; e[4] = e4[2]; e[5] = e4[3];
            uint32_t o[5];
#pragma unroll
            for (int i = 0; i < 5; i++) o[i] = __byte_perm(e[i], e[i + 1], 0x5432);
#pragma unroll
            for (int i = 0; i < 4; i++) {
              uint32_t a = bmul2(o[i], w[h][3]);
              a = bfma2(e[i + 1], w[h][2], a);
              a = bfma2(o[i + 1], w[h][1], a);
              a = bfma2(e[i + 2], w[h][0], a);
              vv[i] = bmul2(a, vv[i]);
            }
            st_async128(ud[h] + uo, ub[h], vv[0], vv[1], vv[2], vv[3]);
          }
          __syncwarp();
        }
        PROF(16);
      }
      {
        const int rw = (lane >> 3) + (lane & 4), ck = lane & 3;
        const uint32_t so = rw * 64 + ck * 16, dof = rw * 128 + ((ck ^ rw) << 4);
        const uint8_t* hsrc = reinterpret_cast<const uint8_t*>(p.ssm_k + (size_t)chb * 8 * SEQ) + so;
        const float dv = lane < 8 ? __bfloat162float(p.ssm_D[chb * 8 + lane]) : 0.f;
        uint32_t x[32];
        auto load = [&](const uint8_t* src, int i) {
          asm volatile("ld.v4.u32 {%0,%1,%2,%3}, [%4];\n" : "=r"(x[4 * i]), "=r"(x[4 * i + 1]), "=r"(x[4 * i + 2]), "=r"(x[4 * i + 3])
                       : "l"(src + i * 512) : "memory");
        };
#pragma unroll
        for (int i = 0; i < 8; i++) load(hsrc + (hw - 1) * 4096, i);
        nb_sync(NB_HELP3, 96);
        mbar_wait(bars + 8 * BAR_U, 0);
        int eh = 0;
#pragma unroll 1
        for (int n = 2 * (hw - 1); n < 16; n += (n & 1) ? 5 : 1) {
          const int c = n >> 1;
          const uint8_t* nsrc = (n & 1) ? hsrc + (c < 5 ? c + 3 : c) * 4096
                                        : smem + OFF_U + c * 4096 + (so ^ (((c ^ (lane >> 2)) & 1) << 6));
          const uint32_t dst = sb + ((n & 1) ? OFF_U : OFF_H) + c * 4096 + dof;
          const float dc = __shfl_sync(0xffffffffu, dv, c);
          const float h0 = bf_lo(x[0]) + ((lane | (n & 1)) == 0 ? dc : 0.f), h1 = bf_hi(x[0]);
          x[0] = pack_bf16(h0, h1);
          uint32_t m[2] = {x[0], x[1]};
#pragma unroll
          for (int i = 2; i < 32; i++) asm("max.xorsign.abs.bf16x2 %0, %0, %1;\n" : "+r"(m[i & 1]) : "r"(x[i]));
          asm("max.xorsign.abs.bf16x2 %0, %0, %1;\n" : "+r"(m[0]) : "r"(m[1]));
          const uint32_t e = max(__reduce_max_sync(0xffffffffu, max((m[0] >> 7) & 255u, (m[0] >> 23) & 255u)), 5u);
          const uint32_t sc = (259u - e) * 0x00800080u;
#pragma unroll
          for (int i = 0; i < 8; i++) {
            uint32_t o[4];
#pragma unroll
            for (int j = 0; j < 4; j++) {
              const uint32_t v = bmul2(x[4 * i + j], sc);
              asm("cvt.rn.f16x2.f32 %0, %1, %2;\n" : "=r"(o[j]) : "f"(bf_hi(v)), "f"(i + j == 0 ? h0 * bf_hi(sc) : bf_lo(v)));
            }
            sts128((dst + (i & 3) * 1024) ^ ((i >> 2) << 6), o[0], o[1], o[2], o[3]);
            load(nsrc, i);
          }
          if (n & 1) {
            const int f = min(max((int)e + eh - 129, 0), 254);
            if (lane == 0) asm volatile("st.shared.u32 [%0], %1;\n" ::"r"(sb + OFF_SC + c * 4), "r"(f << 23) : "memory");
          }
          eh = e;
        }
        fence_async_smem();
        __syncwarp();
        if (lane == 0) mbar_arrive(bars + 8 * BAR_UH);
        PROF(32);
      }
      if (hw < 3) {
        const uint32_t rb = mapa(bars, lane & 1);
        const uint32_t epoch = ld_relaxed(g_flag_o + 2 * cta + hw - 1) + 1;
        const bool own = hw - 1 == (rb2 & 1);
        nb_sync(NB_OREADY + hw - 1, 160);
        if (lane == 0) {
          asm volatile("cp.async.bulk.global.shared::cta.bulk_group [%0], [%1], %2;\n" ::"l"(g_o + (size_t)cta * 16384 + (hw - 1) * 8192),
                       "r"(sb + OFF_OP + (own ? 16384 : 0)), "r"(16384) : "memory");
          bulk_commit();
        }
        if (lane < 2) {
          mbar_arrive_cluster(rb + 8 * (BAR_EMPTY2 + 2));
          mbar_arrive_cluster(rb + 8 * (BAR_EMPTY2 + 3));
        }
        if (lane == 0) {
          bulk_wait0();
          if (own) mbar_expect_tx(bars + 8 * (BAR_FULL2 + 1), 16384);
          mbar_arrive_cluster(mapa(bars, own ? rank : rank ^ 1) + 8 * BAR_X);
          st_release(g_flag_o + 2 * cta + hw - 1, epoch);
          mbar_arrive(bars + 8 * BAR_REL);
        }
        __syncwarp();
        PROF(17);
      } else {
        mbar_wait(bars + 8 * BAR_REL, 0);
        if (MODE == 0) {
          mbar_wait(bars + 8 * BAR_X, 0);
          if (elect_one())
            asm volatile("cp.async.bulk.shared::cluster.shared::cta.mbarrier::complete_tx::bytes [%0], [%1], %2, [%3];\n"
                         ::"r"(mapa(sb + OFF_OP, rank ^ 1)), "r"(sb + OFF_OP + 16384), "r"(16384),
                         "r"(mapa(bars + 8 * BAR_FULL2, rank ^ 1)) : "memory");
        }
        if (MODE == 0) {
          mbar_wait(bars + 8 * BAR_DEAD, 0);
          if (elect_one()) {
            tma_load_3d(sb + g2_b(2), &tmWo, bars + 8 * (BAR_FULL2 + 2), 0, g2_k(hp, 2) * 64, cb2 * 2);
            tma_load_3d(sb + g2_b(3), &tmWo, bars + 8 * (BAR_FULL2 + 3), 0, g2_k(hp, 3) * 64, cb2 * 2);
          }
        }
        __syncwarp();
      }
      {
        const int c8 = (4 * (lr >> 1) + 2 * (lm & 1) + (lr & 1)) & 7;
        const bool own = (lr >> 2) == rank;
        const uint32_t ya = sb + (own ? y_slot(c8 & 1, c8 >> 1) : OFF_LAND + c8 * 2048);
        const uint32_t yx = ((lm >> 1) ^ lr) << 4;
        const int row = (lane >> 3) * 8 + ((lane >> 2) & 1);
        uint2* og = reinterpret_cast<uint2*>(p.out + (size_t)(rank * 1024 + row) * (2 * DM) + (chb & ~1) * 8 + (lane & 3) * 4);
        const uint32_t qa = sb + OFF_Q + lane * 8;
        mbar_wait(bars + 8 * BAR_Q, 0);
        mbar_wait(bars + 8 * BAR_LAND, 0);
        PROF(33);
        const uint32_t t0 = clock();
#pragma unroll 1
        for (int j = hw - 1; j < 16; j += 3) {
          uint32_t y[4][4];
          uint2 q[8];
          while ((uint32_t)clock() - t0 < j * PACE) __nanosleep(40);
          const uint32_t qj = qa + j * 2048;
#pragma unroll
          for (int i = 0; i < 4; i++) ldsm4t(y[i], ya + j * 128 + (yx ^ (i << 5)));
#pragma unroll
          for (int i = 0; i < 8; i++) q[i] = lds64(qj + i * 256);
#pragma unroll
          for (int i = 0; i < 8; i++)
            og[(size_t)(j * 64 + (i >> 2) * 32 + (i & 3) * 2) * (2 * DM / 4)] =
                make_uint2(bmul2(q[i].x, y[i >> 1][2 * (i & 1)]), bmul2(q[i].y, y[i >> 1][2 * (i & 1) + 1]));
        }
      }
      PROF(22);
    }
    cluster_sync_all();
  } else {
    asm volatile("setmaxnreg.inc.sync.aligned.u32 %0;\n" :: "n"(REG_MATH));
    if (warp == 0) PROF2(26);
    const int wg = warp >> 2;
    const int wtid = tid & 127;
    const bool signaller = (wtid == 0) || (wtid == 32);
    const uint32_t rbars = mapa(bars, wtid >> 5 & 1);

    if (halo_cta) {
      const uint32_t epoch = ld_relaxed(g_flag_h + blockIdx.x) + 1;
      float acc0[64], acc1[64];
      int s = 0, ph = 0;
#pragma unroll 1
      for (int kb = 0; kb < 16; kb++) {
        mbar_wait(bars + 8 * (BAR_FULLB + s), ph);
        const uint32_t st = sb + s * STGH;
        const uint64_t da = mkdesc(st, 16, 1024, 1);
        const uint64_t db = mkdesc(st + 8192 + wg * 32768, 8192, 1024, 1);
        wg_fence();
#pragma unroll
        for (int kk = 0; kk < 4; kk++) {
          wgmma_n128(acc0, da + 2 * kk, db + 128 * kk, kb + kk);
          wgmma_n128(acc1, da + 2 * kk, db + 1024 + 128 * kk, kb + kk);
        }
        wg_commit();
        wg_wait<0>();
        if (wtid == 0) mbar_arrive(bars + 8 * (BAR_EMPTYB + s));
        if (++s == 3) { s = 0; ph ^= 1; }
      }
      fence_regs(acc0);
      fence_regs(acc1);
      if ((warp & 3) != 3) {
#pragma unroll
        for (int hh = 0; hh < 2; hh++) {
          uint4* dst = g_halo + ((hh * 4 + (warp & 3) + 1) * 16 + blockIdx.x * 4) * 128 + wg * 64 + lane;
#pragma unroll
          for (int j = 0; j < 4; j++) {
            const int o = 16 * j + 2 * hh;
            dst[(j >> 1) * 128 + (j & 1) * 32] =
                make_uint4(pack_bf16(acc0[o], acc0[o + 1]), pack_bf16(acc0[o + 4], acc0[o + 5]),
                           pack_bf16(acc0[o + 8], acc0[o + 9]), pack_bf16(acc0[o + 12], acc0[o + 13]));
            dst[(2 + (j >> 1)) * 128 + (j & 1) * 32] =
                make_uint4(pack_bf16(acc1[o], acc1[o + 1]), pack_bf16(acc1[o + 4], acc1[o + 5]),
                           pack_bf16(acc1[o + 8], acc1[o + 9]), pack_bf16(acc1[o + 12], acc1[o + 13]));
          }
        }
      }
      nb_sync(NB_G1DONE, 256);
      if (tid == 0) st_release(g_flag_h + blockIdx.x, epoch);
      PROF(36);
      cluster_sync_all();
      return;
    }

    if (MODE != 2) {
    {
      float acc0[96], acc1[96];
      int sa = 0, pha = 0, sbb = 0, phb = 0;
      asm volatile("cp.async.wait_group 0;\n" ::: "memory");
      fence_async_smem();
      nb_sync(NB_FIRST, 256);
      if (tid == 0) {
        mbar_arrive(bars + 8 * BAR_FULLA);
        mbar_arrive(bars + 8 * BAR_FULLB);
      }
      PROF(0 + wg);
#pragma unroll 1
      for (int kb = 0; kb < 30; kb++) {
        if (!(kb & 1)) mbar_wait(bars + 8 * (BAR_FULLA + sa), pha);
        mbar_wait(bars + 8 * (BAR_FULLB + sbb), phb);
        if (kb == 0) PROF2(0 + wg);
        if (kb == 4 && wg == 0) PROF2(28);
        if (kb == 8 && wg == 0) PROF2(29);
        if (kb == 16 && wg == 0) PROF2(30);
        const uint64_t da = mkdesc(sb + sa * STG1A + wg * 16384 + (kb & 1) * 64, 16, 1024, 1);
        const uint64_t db = mkdesc(sb + OFF_1B + sbb * STG1B, 4096, 1024, 1);
        wg_fence();
        wgmma_n192(acc0, da, db, kb);
        wgmma_n192(acc1, da + 512, db, kb);
        wgmma_n192(acc0, da + 2, db + 128, 1);
        wgmma_n192(acc1, da + 514, db + 128, 1);
        wg_commit();
        wg_wait<1>();
        if (kb > 0) {
          if (wtid == 64) mbar_arrive(bars + 8 * (BAR_EMPTYB + (sbb == 0 ? NS1B - 1 : sbb - 1)));
          if (!(kb & 1) && signaller) mbar_arrive_cluster(rbars + 8 * (BAR_EMPTYA + (sa == 0 ? NS1A - 1 : sa - 1)));
        }
        if (++sbb == NS1B) { sbb = 0; phb ^= 1; }
        if ((kb & 1) && ++sa == NS1A) { sa = 0; pha ^= 1; }
      }
      const int blk0 = wg * 8 + (warp & 3);
      const int lr = lane & 7, lm = lane >> 3;
      const bool le0 = 2 * (lane & 3) <= (lane >> 2), le1 = 2 * (lane & 3) + 1 <= (lane >> 2);
      const uint32_t maskLE = (le0 ? 0x0000FFFFu : 0u) | (le1 ? 0xFFFF0000u : 0u);
      uint32_t k0[2][2][4], k1[2][2][4], qa[2][2][8];
      float l[2][2][4];
      {
        static_assert(15 % NS1A == 0 && 30 % NS1B == 0, "slots of the last k blocks");
        mbar_wait(bars + 8 * BAR_FULLA, 1);
        mbar_wait(bars + 8 * BAR_FULLB, 0);
        mbar_wait(bars + 8 * (BAR_FULLB + 1), 0);
        const uint64_t da = mkdesc(sb + wg * 16384, 16, 1024, 1);
        const uint64_t db = mkdesc(sb + OFF_1B, 4096, 1024, 1);
        wg_fence();
#pragma unroll
        for (int i = 0; i < 4; i++) wgmma_n192(acc0, da + 2 * i, db + (i >> 1) * (STG1B >> 4) + (i & 1) * 128, 1);
        wg_commit();
        wg_wait<1>();
        if (wtid == 64) mbar_arrive(bars + 8 * (BAR_EMPTYB + NS1B - 1));
#pragma unroll
        for (int i = 0; i < 2; i++) wgmma_n192(acc1, da + 512 + 2 * i, db + (i >> 1) * (STG1B >> 4) + (i & 1) * 128, 1);
        wg_commit();
        wg_wait<1>();
        fence_regs(acc0);
        attn_stage(sb, blk0, lane, acc0, k1[0]);
#pragma unroll
        for (int i = 2; i < 4; i++) wgmma_n192(acc1, da + 512 + 2 * i, db + (i >> 1) * (STG1B >> 4) + (i & 1) * 128, 1);
        wg_commit();
        attn_pack(acc0, qa[0], k0[0]);
        wg_wait<0>();
        fence_regs(acc1);
      }
      if (wtid == 64) mbar_arrive(bars + 8 * BAR_EMPTYB);
      PROF(2 + wg);
      attn_stage(sb, blk0 + 4, lane, acc1, k1[1]);
      __syncwarp();
      if (lane == 0) mbar_arrive(bars + 8 * BAR_STG);
      mbar_wait(bars + 8 * BAR_U, 0);
      attn_pack(acc1, qa[1], k0[1]);
      attn_own(k0[0], k1[0], le0, le1, qa[0], l[0]);
      attn_own(k0[1], k1[1], le0, le1, qa[1], l[1]);
      const uint32_t cho[2] = {(uint32_t)(((lm & 1) ^ lr) << 4), (uint32_t)(((2 + (lm & 1)) ^ lr) << 4)};
      const uint32_t obase = sb + OFF_OP + (wg == (rb2 & 1) ? 16384 : 0) + ((warp & 3) * 16 + lr) * 128;
      mbar_wait(bars + 8 * BAR_STG, 0);
      {
        uint32_t km[4][4], va[8][4], vb[8][4], pp[8];
        float x[8][2];
#pragma unroll
        for (int n = 0; n < 4; n++) {
          const int blk = blk0 + 4 * (n >> 1);
          to_arr(km[n], lds128(sb + (blk == 0 ? OFF_L0 + 1024 : OFF_KH + (blk - 1) * 2048) + (n & 1) * 512 + lane * 16));
        }
#pragma unroll
        for (int n = 0; n < 8; n++) {
          const int vr = (blk0 + 4 * ((n >> 1) & 1)) * 16 - 8 + 8 * (n >> 2) + 8 * (lm >> 1);
          const uint32_t vrow = sb + (vr < 0 ? OFF_L0 : OFF_VP + vr * 128) + lr * 128;
          ldsm4t(va[n], vrow + (cho[0] ^ ((n & 1) << 6)));
          ldsm4t(vb[n], vrow + (cho[1] ^ ((n & 1) << 6)));
        }
        const bool first = blk0 == 0 && gidx == 0;
#pragma unroll
        for (int n = 0; n < 4; n++) {
          const uint32_t(&q)[8] = qa[n >> 1][n & 1];
          float sm[4];
          mma16816_z(sm, q[0], q[1], q[2], q[3], km[n][0], km[n][1]);
          mma16816(sm, q[4], q[5], q[6], q[7], km[n][2], km[n][3]);
          if (n < 2 && first) sm[0] = sm[1] = -1e9f / 0.17677669529663687f;
          x[n][0] = le0 ? l[n >> 1][n & 1][0] : sm[0];
          x[n][1] = le1 ? l[n >> 1][n & 1][1] : sm[1];
          x[4 + n][0] = l[n >> 1][n & 1][2];
          x[4 + n][1] = l[n >> 1][n & 1][3];
        }
        quad_softmax<8>(x, pp);
#pragma unroll
        for (int n = 7; n >= 0; n--)
          attn_pv(obase + ((n >> 1) & 1) * 8192 + (n >> 2) * 1024 + (((4 * (n & 1) + lm) ^ lr) << 4), va[n], vb[n], pp[n],
                  maskLE);
      }
      fence_async_smem();
      nb_arrive(NB_OREADY + wg, 160);
    }

    {
      const int w = warp & 3;
      uint32_t a1[2][4], a4[8][4], tw[16], d1[32];
      float d4[16];
      const uint32_t tb = sb + OFF_T + wtid * 16;
      PROF(34 + wg);
      mbar_wait(bars + 8 * BAR_T, 0);
      mbar_wait(bars + 8 * BAR_UH, 0);
      to_arr(a1[0], lds128(tb + T_A1));
      to_arr(a1[1], lds128(tb + T_A1 + 2048));
      const uint64_t dx = mkdesc(sb + OFF_U + wg * 4096, OFF_H - OFF_U, 1024, 1);
      const uint64_t dz = mkdesc(sb + OFF_U + wg * 4096, 512, 128, 0);
      const uint64_t db2 = mkdesc(sb + OFF_T + T_B2, 128, 256, 0);
      wg_fence();
      hmma_n128t<0>(d1, a1[0], dx);
      hmma_n128t<1>(d1, a1[1], dx + 128);
      wg_commit();
      auto ldtw = [&](int i) {
        const uint4 v = lds128(tb + T_TW + i * 2048);
        tw[4 * i] = v.x; tw[4 * i + 1] = v.y; tw[4 * i + 2] = v.z; tw[4 * i + 3] = v.w;
      };
      ldtw(0);
      ldtw(1);
      const uint32_t za = sb + (w < 2 ? OFF_U : OFF_H) + wg * 4096 + (w & 1) * 2048 + lane * 16;
      const uint32_t yl = (wtid ^ (4 * rank + wg)) * 16;
      const uint32_t yown = mapa(sb, rank) + yl, yrem = mapa(sb + OFF_LAND + wg * 2048, rank ^ 1) + yl;
      const uint32_t yb[2] = {mapa(bars + 8 * BAR_LAND, 0), mapa(bars + 8 * BAR_LAND, 1)};
      wg_wait<0>();
      fence_regs(d1);
      nb_sync(NB_WG + wg, 128);
      auto s4 = [&](int it) {
        wg_fence();
#pragma unroll
        for (int ks = 0; ks < 8; ks++) {
          const uint64_t d = dz + (it & 1) * 512 + (ks & 3) * 64 + (ks >> 2) * ((OFF_H - OFF_U) >> 4);
          if (ks == 0) fmma_n32t<0>(d4, a4[ks], d);
          else fmma_n32t<1>(d4, a4[ks], d);
        }
        wg_commit();
      };
      auto e4 = [&](int it) {
        fence_regs(d4);
        const float sc = __uint_as_float(lds32(sb + OFF_SC + wg * 4 + it * 8));
        uint32_t r[8];
#pragma unroll
        for (int i = 0; i < 8; i++) r[i] = pack_bf16(d4[2 * i] * sc, d4[2 * i + 1] * sc);
        const uint32_t o = (yown + y_slot(wg, it)) ^ ((it >> 1) << 5), m = (yrem + it * 4096) ^ ((it >> 1) << 5);
        if (it == 0) mbar_wait(bars + 8 * BAR_LFREE, 0);
        if (it == 3) mbar_wait(bars + 8 * (BAR_DEAD + 1), 0);
        st_async128(rank ? m : o, yb[0], r[0], r[2], r[1], r[3]);
        st_async128(rank ? o : m, yb[1], r[4], r[6], r[5], r[7]);
      };
      uint32_t a2[2][2][2][4], a3[2][2][4], d2[2][2][8], d3[2][8];
      auto s2a = [&]() {
        wg_fence();
#pragma unroll
        for (int c = 0; c < 4; c++) hmma_n32<0, 0>(d2[c & 1][c >> 1], a2[0][c & 1][c >> 1], db2 + (c >> 1) * 128);
      };
      auto s2b = [&]() {
        wg_fence();
#pragma unroll
        for (int c = 0; c < 4; c++) {
          hmma_n32<1, 0>(d2[c & 1][c >> 1], a2[1][c & 1][c >> 1], db2 + (c >> 1) * 128 + 64);
          if (c & 1) wg_commit();
        }
      };
      auto s1 = [&](int it) {
        hmma_n128t<0>(d1, a1[0], dx + it * 512);
        hmma_n128t<1>(d1, a1[1], dx + it * 512 + 128);
        wg_commit();
      };
      auto done = [&](int it) {
        if (it == 0) {
          if (signaller) mbar_arrive_cluster(rbars + 8 * BAR_LFREE);
        } else if (it >= 2 && wtid == 64) {
          mbar_arrive(bars + 8 * (BAR_DEAD + it - 2));
        }
        if (w == 0) PROF3(40 + 4 * wg + it);
      };
      fft_e1<0>(d1, tw, a2[0]);
      s2a();
      fft_e1<1>(d1, tw, a2[1]);
      s2b();
      s1(1);
      ldtw(2);
      ldtw(3);
#pragma unroll
      for (int i = 0; i < 8; i++) to_arr(a4[i], lds128(tb + T_A4 + i * 2048));
#pragma unroll
      for (int it = 0; it < 4; it++) {
        if (it == 0 || it == 3) wg_wait<2>(); else wg_wait<3>();
        fence_regs(d2[0][0]);
        fence_regs(d2[1][0]);
        fft_e2<0, 0>(d2[0][0], d2[1][0], a3[0]);
        fft_e2<0, 1>(d2[0][0], d2[1][0], a3[1]);
        if (it == 0 || it == 3) wg_wait<1>(); else wg_wait<2>();
        fence_regs(d2[0][1]);
        fence_regs(d2[1][1]);
        fft_e2<1, 0>(d2[0][1], d2[1][1], a3[0]);
        fft_e2<1, 1>(d2[0][1], d2[1][1], a3[1]);
        wg_fence();
        hmma_n32<0, 0>(d3[0], a3[0][0], db2);
        hmma_n32<0, 0>(d3[1], a3[0][1], db2);
        hmma_n32<1, 0>(d3[0], a3[1][0], db2 + 64);
        hmma_n32<1, 0>(d3[1], a3[1][1], db2 + 64);
        wg_commit();
        wg_wait<1>();
        if (it > 0) e4(it - 1);
        if (it < 3) {
          fence_regs(d1);
          fft_e1<0>(d1, tw, a2[0]);
        }
        wg_wait<0>();
        fence_regs(d3[0]);
        fence_regs(d3[1]);
        if (it < 3) s2a();
        fft_e3(d3, tw, za + (it & 1) * 8192);
        if (it < 3) {
          fft_e1<1>(d1, tw, a2[1]);
          s2b();
        }
        fence_async_smem();
        nb_sync(NB_WG + wg, 128);
        done(it);
        s4(it);
        if (it < 2) s1(it + 2);
      }
      wg_wait<0>();
      if (signaller) mbar_arrive_cluster(rbars + 8 * (BAR_EMPTY2 + 4));
      e4(3);
      PROF(6 + wg);
    }
    }

    if (MODE != 1) {
      float acc[64];
      int s = 0, ph = 0;
#pragma unroll 1
      for (int kb = 0; kb < 16; kb++) {
        mbar_wait(bars + 8 * (BAR_FULL2 + s), ph);
        if (kb == 0) PROF(8 + wg);
        if (warp == 4) PROF2(40 + kb);
        const uint64_t da = mkdesc(sb + g2_a(s) + wg * 8192, 16, 1024, 1);
        const uint64_t db = mkdesc(sb + g2_b(s), 8192, 1024, 1);
        wg_fence();
        wgmma_n128(acc, da, db, kb);
        wgmma_n128(acc, da + 2, db + 128, 1);
        wgmma_n128(acc, da + 4, db + 256, 1);
        wgmma_n128(acc, da + 6, db + 384, 1);
        wg_commit();
        wg_wait<0>();
        if (kb < 16 - NS2 && signaller) mbar_arrive_cluster(rbars + 8 * (BAR_EMPTY2 + s));
        if (++s == NS2) { s = 0; ph ^= 1; }
      }
      wg_wait<0>();
      fence_regs(acc);
      PROF(10 + wg);
      const int lr = lane & 7, lm = lane >> 3;
      const uint32_t wbase = sb + warp * 2048;
      const uint32_t base = wbase + (lr + 8 * (lm & 1)) * 128;
#pragma unroll
      for (int j = 0; j < 16; j += 2) {
        const uint32_t a = base + (j >> 3) * 16384 + ((((j & 7) + (lm >> 1)) ^ lr) << 4);
        stsm4(a, pack_bf16(acc[4 * j], acc[4 * j + 1]), pack_bf16(acc[4 * j + 2], acc[4 * j + 3]),
              pack_bf16(acc[4 * j + 4], acc[4 * j + 5]), pack_bf16(acc[4 * j + 6], acc[4 * j + 7]));
      }
      __syncwarp();
      {
        const int rr = lane >> 4, ck = lane & 7, hf = (lane >> 3) & 1;
        uint4* og = reinterpret_cast<uint4*>(p.out + (size_t)(2 * ((rb2 & 7) * 128 + warp * 16 + rr) + (rb2 >> 3)) * (2 * DM) + DM + cb2 * 128 + hf * 64 + ck * 8);
        uint4 v[8];
#pragma unroll
        for (int i = 0; i < 8; i++) v[i] = lds128(wbase + hf * 16384 + (2 * i + rr) * 128 + ((ck ^ ((2 * i + rr) & 7)) << 4));
#pragma unroll
        for (int i = 0; i < 8; i++) og[(size_t)i * 4 * (2 * DM / 8)] = v[i];
      }
      PROF(12 + wg);
    }
    cluster_sync_all();
  }
}

typedef CUresult (*EncodeFn)(CUtensorMap*, CUtensorMapDataType, cuuint32_t, void*, const cuuint64_t*, const cuuint64_t*,
                             const cuuint32_t*, const cuuint32_t*, CUtensorMapInterleave, CUtensorMapSwizzle,
                             CUtensorMapL2promotion, CUtensorMapFloatOOBfill);

void make_map(EncodeFn enc, CUtensorMap* tm, const void* base, int rank, const cuuint64_t* dims, const cuuint64_t* strides,
              const cuuint32_t* box, CUtensorMapSwizzle swz) {
  cuuint32_t es[5] = {1, 1, 1, 1, 1};
  enc(tm, CU_TENSOR_MAP_DATA_TYPE_BFLOAT16, rank, const_cast<void*>(base), dims, strides, box, es,
      CU_TENSOR_MAP_INTERLEAVE_NONE, swz, CU_TENSOR_MAP_L2_PROMOTION_L2_256B, CU_TENSOR_MAP_FLOAT_OOB_FILL_NONE);
}

}

extern "C" void kernel_launch(void* const* d_in, const int* in_sizes, int n_in, void* d_out, int out_size) {
  static EncodeFn enc = nullptr;
  static bool coresident = true;
  if (!enc) {
    void* fn = nullptr;
    cudaDriverEntryPointQueryResult qr;
    cudaGetDriverEntryPoint("cuTensorMapEncodeTiled", &fn, cudaEnableDefault, &qr);
    enc = (EncodeFn)fn;
    cudaFuncSetAttribute(fused_kernel<0>, cudaFuncAttributeMaxDynamicSharedMemorySize, SMEM_BYTES);
    cudaFuncSetAttribute(fused_kernel<1>, cudaFuncAttributeMaxDynamicSharedMemorySize, SMEM_BYTES);
    cudaFuncSetAttribute(fused_kernel<2>, cudaFuncAttributeMaxDynamicSharedMemorySize, SMEM_BYTES);
    cudaLaunchConfig_t cfg = {};
    cfg.gridDim = dim3(NCTA);
    cfg.blockDim = dim3(NTHREADS);
    cfg.dynamicSmemBytes = SMEM_BYTES;
    cudaLaunchAttribute at;
    at.id = cudaLaunchAttributeClusterDimension;
    at.val.clusterDim.x = 2;
    at.val.clusterDim.y = 1;
    at.val.clusterDim.z = 1;
    cfg.attrs = &at;
    cfg.numAttrs = 1;
    int nclusters = 0;
    if (cudaOccupancyMaxActiveClusters(&nclusters, fused_kernel<0>, &cfg) == cudaSuccess) coresident = nclusters >= NCTA / 2;
    (void)cudaGetLastError();
  }
  CUtensorMap tmX, tmW, tmWo, tmQ, tmXh, tmWh;
  {
    cuuint64_t dims[3] = {1024, 2, 1024};
    cuuint64_t str[2] = {2048, 4096};
    cuuint32_t box[3] = {64, 1, 128};
    make_map(enc, &tmX, d_in[6], 3, dims, str, box, CU_TENSOR_MAP_SWIZZLE_128B);
  }
  {
    cuuint64_t dims[3] = {1024, 1024, 3};
    cuuint64_t str[2] = {6144, 2048};
    cuuint32_t box[3] = {64, 32, 3};
    make_map(enc, &tmW, d_in[7], 3, dims, str, box, CU_TENSOR_MAP_SWIZZLE_128B);
  }
  {
    cuuint64_t dims[3] = {64, 1024, 16};
    cuuint64_t str[2] = {2048, 128};
    cuuint32_t box[3] = {64, 64, 2};
    make_map(enc, &tmWo, d_in[8], 3, dims, str, box, CU_TENSOR_MAP_SWIZZLE_128B);
  }
  {
    cuuint64_t dims[5] = {1024, 2, 4, 4, 64};
    cuuint64_t str[4] = {2048, 8 * 2048, 2 * 2048, 32 * 2048};
    cuuint32_t box[5] = {16, 2, 4, 4, 4};
    make_map(enc, &tmQ, d_in[0], 5, dims, str, box, CU_TENSOR_MAP_SWIZZLE_NONE);
  }
  {
    cuuint64_t dims[4] = {1024, 256, 2, 4};
    cuuint64_t str[3] = {4096, 2048, 256 * 4096};
    cuuint32_t box[4] = {64, 8, 2, 4};
    make_map(enc, &tmXh, d_in[6], 4, dims, str, box, CU_TENSOR_MAP_SWIZZLE_128B);
  }
  {
    cuuint64_t dims[3] = {64, 1024, 48};
    cuuint64_t str[2] = {6144, 128};
    cuuint32_t box[3] = {64, 64, 4};
    make_map(enc, &tmWh, d_in[7], 3, dims, str, box, CU_TENSOR_MAP_SWIZZLE_128B);
  }
  Params p;
  p.q = (const __nv_bfloat16*)d_in[0];
  p.k = (const __nv_bfloat16*)d_in[1];
  p.v = (const __nv_bfloat16*)d_in[2];
  p.shift_k = (const __nv_bfloat16*)d_in[3];
  p.ssm_k = (const __nv_bfloat16*)d_in[4];
  p.ssm_D = (const __nv_bfloat16*)d_in[5];
  p.x = (const __nv_bfloat16*)d_in[6];
  p.w = (const __nv_bfloat16*)d_in[7];
  p.wo = (const __nv_bfloat16*)d_in[8];
  p.out = (__nv_bfloat16*)d_out;
  if (coresident) {
    fused_kernel<0><<<NCTA, NTHREADS, SMEM_BYTES>>>(p, tmX, tmW, tmWo, tmQ, tmXh, tmWh);
  } else {
    fused_kernel<0><<<4, NTHREADS, SMEM_BYTES>>>(p, tmX, tmW, tmWo, tmQ, tmXh, tmWh);
    fused_kernel<1><<<NCTA, NTHREADS, SMEM_BYTES>>>(p, tmX, tmW, tmWo, tmQ, tmXh, tmWh);
    fused_kernel<2><<<NCTA, NTHREADS, SMEM_BYTES>>>(p, tmX, tmW, tmWo, tmQ, tmXh, tmWh);
  }
}
```

```cpp
#include <cuda_runtime.h>
#include <cuda.h>
#include <cuda_bf16.h>
#include <stdint.h>

namespace {

constexpr int SEQ = 2048;
constexpr int DM = 1024;
constexpr int NCTA = 132;
constexpr int NTHREADS = 384;

constexpr int STG1A = 32768;
constexpr int NS1A = 3;
constexpr int STG1B = 12288;
constexpr int NS1B = 5;
constexpr int OFF_1B = NS1A * STG1A;
constexpr int STG2 = 32768;
constexpr int NS2 = 5;
constexpr int STGH = 73728;
constexpr int OFF_VP = 0;
constexpr int OFF_KH = 1 * STG2;
constexpr int OFF_OP = 2 * STG2;
constexpr int OFF_Q = 3 * STG2;
constexpr int T_A4 = 0, T_TW = 16384, T_B2 = 24576, T_A1 = 28672, T_END = 32768;
constexpr int OFF_U = 163840;
constexpr int OFF_H = OFF_U + 32768;
constexpr int OFF_T = OFF_U - T_END;
constexpr int OFF_LAND = 4 * STG2;
constexpr int OFF_BAR = OFF_H + 32768;
constexpr int OFF_SC = OFF_BAR + 512;
constexpr int OFF_L0 = OFF_BAR + 1024;
constexpr int SMEM_BYTES = OFF_L0 + 2048;
static_assert(OFF_T + T_A1 == OFF_1B + NS1B * STG1B && OFF_T + T_TW == OFF_1B + 4 * STG1B && OFF_LAND == OFF_T + T_A4, "layout");
static_assert(3 * STGH <= OFF_BAR && SMEM_BYTES <= 232448, "smem");

constexpr int BAR_FULLA = 0;
constexpr int BAR_EMPTYA = 3;
constexpr int BAR_FULLB = 6;
constexpr int BAR_EMPTYB = 11;
constexpr int BAR_FULL2 = 16;
constexpr int BAR_EMPTY2 = 21;
constexpr int BAR_T = 26;
constexpr int BAR_UH = 27;
constexpr int BAR_LFREE = 28;
constexpr int BAR_LAND = 29;
constexpr int BAR_U = 30;
constexpr int BAR_Q = 31;
constexpr int BAR_STG = 32;
constexpr int BAR_DEAD = 33;
constexpr int BAR_X = 35;
constexpr int BAR_REL = 36;

constexpr int NB_G1DONE = 1;
constexpr int NB_OREADY = 2;
constexpr int NB_WG = 4;
constexpr int NB_HELP3 = 6;
constexpr int NB_FIRST = 7;

#define PACE 480u
#define PF0 20
#define EARLYS1 1
#define PEEL 1
#define IDLEW 1
#define SCHED 1
#define REG_MATH 224
#define REG_HELP 56
constexpr int SPIN_LIMIT = 1 << 20;

__device__ __align__(1024) __nv_bfloat16 g_o[SEQ * DM];
__device__ uint32_t g_flag_o[256];
__device__ uint32_t g_flag_h[4];
__device__ uint4 g_halo[128 * 128];
__device__ __align__(128) const uint32_t g_tab[T_END / 4] = {
0x3c003c00,0x3bf13bff,0,0xafd6a648,0x3c003c00,0x3b993bce,0,0xb505b303,0x3c003c00,0x3af63b50,0,0xb7e3b67c,
0x3c003c00,0x3a0f3a8a,0,0xb93ab89b,0x3bc33bfe,0x3b773bfa,0xb3c6aa48,0xb5c2acb5,0x3a6d3b3b,0x389b3a4f,0xb8c4b6d7,0xba8ab8ec,
0x381d395f,0x26483505,0xbaddb9ed,0xbbffbb99,0x30b23564,0xb848b444,0xbbeabb88,0xbac2bbb6,0x3b0e3bf6,0x3a8a3bf1,0xb78bae46,0xb89bafd6,
0x34a53913,0xa6483732,0xbba8ba2f,0xbbffbb25,0xb78bae46,0xbac2b7e3,0xbb0ebbf6,0xb848baf6,0xbba8ba2f,0xbb50bbfa,0xb4a5b913,0x367cacb5,
0x39ed3bea,0x393a3be2,0xb95fb0b2,0xba0fb179,0xb56433c6,0xb8ec2648,0xbb88bbc3,0xba4fbbff,0xbbfeba6d,0xbb25bbce,0xaa48b8c4,0x3732b303,
0xb6d7badd,0x3444b67c,0x3b3b381d,0x3bb63b50,0x38723bd9,0x37323bce,0xbaa7b23e,0xbb25b303,0xbaa7b23e,0xbbb6b67c,0xb872bbd9,0xb444bb50,
0xb872bbd9,0xacb5ba8a,0x3aa7323e,0x3bfa389b,0x3aa7323e,0x3bf139cb,0x38723bd9,0xafd63984,0x35643bc3,0x33033bb6,0xbb88b3c6,0xbbceb444,
0xbbfeb8c4,0xbb77ba0f,0x2a48ba6d,0x35c2b93a,0x36d7b81d,0x3a8aafd6,0x3b3b3add,0x389b3bf1,0x395f3bea,0x26483b25,0xb9ed30b2,0xbbffb732,
0x2e463ba8,0xa6483b99,0xbbf6b4a5,0xbbffb505,0xba2fbb0e,0xb848bbb6,0x3913b78b,0x3ac2b444,0x3bf634a5,0x3b50393a,0x2e463ba8,0xb67c3a0f,
0xb913378b,0xbbe2afd6,0xba2fbb0e,0xb179bbf1,0xb0b23b88,0xb4443b77,0xbbeab564,0xbbb6b5c2,0xb3c6bbfe,0x2cb5bbe2,0x3bc3aa48,0x3bfa3179,
0x38c43b3b,0x2fd63bff,0xba6d36d7,0xbbf12648,0xbaddb95f,0xb505bbce,0x381db9ed,0x3b99b303,0xb61f3b64,0xb7e33b50,0xbb64b61f,0xbaf6b67c,
0x361fbb64,0x393aba8a,0x3b64361f,0x3a0f389b,0xb61f3b64,0xba4f3984,0xbb64b61f,0xb8ecb9cb,0x361fbb64,0x3b25b848,0x3b64361f,0x37323ac2,
0xb8c43b3b,0xb9843b25,0xba6db6d7,0xb9cbb732,0x3addb95f,0x3bceb7e3,0x381d39ed,0x33033af6,0xbbea3564,0xbb77acb5,0xb0b2bb88,0x35c2bbfa,
0x3bc32a48,0x389b38ec,0xb3c63bfe,0xba8a3a4f,0xba2f3b0e,0xbac23af6,0xb913b78b,0xb848b7e3,0x3bf6b4a5,0x3b50acb5,0xae463ba8,0xb67c3bfa,
0xb913b78b,0xb179ba4f,0x3a2fbb0e,0x3be2b8ec,0xae463ba8,0xb9cb3b99,0xbbf634a5,0xb984b505,0xbb3b3add,0xbb993ac2,0xb6d7b81d,0xb505b848,
0x39ed30b2,0x37e335c2,0xb95f3bea,0xbaf63b77,0x3564bbc3,0x3a0fbbe2,0x3b88b3c6,0x393a3179,0xbbfe38c4,0xba4f2648,0xaa48ba6d,0x38ecbbff,
0xbbd93aa7,0xbbfa3a8a,0xb23eb872,0xacb5b89b,0x323e3872,0xafd639cb,0xbbd93aa7,0xbbf13984,0x3bd9baa7,0x3b99b848,0x323e3872,0xb5053ac2,
0xb23eb872,0x37e3bb77,0x3bd9baa7,0x3af6b5c2,0xbbfe3a6d,0xbbe23a4f,0x2a48b8c4,0x3179b8ec,0xb6d73add,0xb9843b99,0xbb3b381d,0xb9cb3505,
0x395fb0b2,0x33033444,0xb9ed3bea,0xbbce3bb6,0x3b88bbc3,0x3b77b93a,0x356433c6,0xb5c23a0f,0xbba83a2f,0xbb503a0f,0x34a5b913,0x367cb93a,
0xbb0e3bf6,0xbbe23bf1,0xb78b2e46,0xb179afd6,0xb4a53913,0xb9cb3b25,0xbba83a2f,0xb9843732,0x378bae46,0xb30337e3,0xbb0e3bf6,0xbbce3af6,
0xbadd39ed,0xba4f39cb,0x381db95f,0x38ecb984,0xbbea3b88,0xbb253ac2,0x30b2b564,0x3732b848,0xbbc33bfe,0xbbb63b77,0xb3c62a48,0x3444b5c2,
0xba6d3b3b,0xbbfa3be2,0xb8c436d7,0x2cb5b179,0xb9a839a8,0xb8ec3984,0x39a8b9a8,0x3a4fb9cb,0xb9a839a8,0xb7323848,0x39a8b9a8,0x3b25bac2,
0xb9a839a8,0xb44435c2,0x39a8b9a8,0x3bb6bb77,0xb9a839a8,0xacb53179,0x39a8b9a8,0x3bfabbe2,0xb81d395f,0xb67c393a,0x3addb9ed,0x3b50ba0f,
0xb0b23564,0x31792fd6,0x3beabb88,0x3be2bbf1,0x33c6aa48,0x3984b732,0x3bc3bbfe,0x39cbbb25,0x38c4b6d7,0x3bcebaf6,0x3a6dbb3b,0x3303b7e3,
0xb4a53913,0xb17938ec,0x3ba8ba2f,0x3be2ba4f,0x378bae46,0x39cbb505,0x3b0ebbf6,0x3984bb99,0x3ba8ba2f,0x3bcebbb6,0x34a5b913,0xb303b444,
0x3b0ebbf6,0x35c2ba0f,0xb78b2e46,0xbb77393a,0xaa4838c4,0x2cb5389b,0x3bfeba6d,0x3bfaba8a,0x3b3bb81d,0x3bf1b984,0x36d7badd,0x2fd6b9cb,
0x39edbbea,0x3505bac2,0xb95f30b2,0xbb993848,0xb564b3c6,0xbaf635c2,0xbb883bc3,0xb7e33b77,0x323e3872,0x35053848,0x3bd9baa7,0x3b99bac2,
0x3bd9baa7,0x3af6bb77,0xb23eb872,0xb7e3b5c2,0xb23eb872,0xb93ab179,0xbbd93aa7,0xba0f3be2,0xbbd93aa7,0xb8ec3bff,0x323e3872,0x3a4fa648,
0x36d7381d,0x384837e3,0x3b3bbadd,0x3ac2baf6,0x395fbbea,0x367cbbfa,0xb9edb0b2,0xbb502cb5,0xbb8833c6,0xbbe238ec,0xb5643bc3,0x31793a4f,
0x2a483a6d,0x39843505,0x3bfeb8c4,0x39cbbb99,0x3913378b,0x39cb3732,0x3a2fbb0e,0x3984bb25,0x2e46bba8,0xb303baf6,0xbbf634a5,0xbbce37e3,
0xba2f3b0e,0xb5c23bfa,0x3913378b,0x3b772cb5,0x3bf6b4a5,0x3a8aba4f,0x2e46bba8,0xb89bb8ec,0x3a6d36d7,0x3af6367c,0x38c4bb3b,0x37e3bb50,
0xb81db9ed,0xba0fb89b,0xbadd395f,0xb93a3a8a,0x30b23b88,0x38ec39cb,0x3beab564,0x3a4fb984,0x33c6bbfe,0xb732bac2,0xbbc3aa48,0xbb253848,
0x3b64361f,0x3bb635c2,0x361fbb64,0x3444bb77,0xbb64b61f,0xbbfab179,0xb61f3b64,0xacb53be2,0x3b64361f,0x3bf1a648,0x361fbb64,0xafd6bbff,
0xbb64b61f,0xbb993303,0xb61f3b64,0x35053bce,0x3bea3564,0x3bff3505,0x30b2bb88,0x2648bb99,0xbbc32a48,0xbac23444,0x33c63bfe,0x38483bb6,
0x3a6db6d7,0x367cba0f,0xb8c4bb3b,0xbb50b93a,0xb81d39ed,0x31793bf1,0x3add395f,0x3be22fd6,0x3bf634a5,0x3bce3444,0xae46bba8,0xb303bbb6,
0xb913378b,0xb5c2393a,0x3a2f3b0e,0x3b773a0f,0xae46bba8,0xb89bbbf1,0xbbf6b4a5,0xba8a2fd6,0x3a2f3b0e,0x3bff3732,0x3913b78b,0xa648bb25,
0x3b8833c6,0x3b253303,0xb564bbc3,0xb732bbce,0xaa483a6d,0x34443b50,0x3bfe38c4,0x3bb6367c,0xbb3bbadd,0xbbfab89b,0xb6d7381d,0x2cb53a8a,
0x39edb0b2,0x2fd6b984,0xb95fbbea,0xbbf1b9cb,0x3aa7323e,0x3a0f3179,0xb872bbd9,0xb93abbe2,0x38723bd9,0x3a4f3bff,0x3aa7323e,0x38eca648,
0xbaa7b23e,0xb7323303,0x38723bd9,0x3b253bce,0xb872bbd9,0xbbb6bb50,0xbaa7b23e,0xb444367c,0x395f30b2,0x389b2fd6,0xb9edbbea,0xba8abbf1,
0x3b883bc3,0x3bff3b25,0x3564b3c6,0x2648b732,0x2a4838c4,0x38483af6,0x3bfe3a6d,0x3ac237e3,0xbb3bb81d,0xb67c2cb5,0x36d73add,0x3b503bfa,
0x378b2e46,0x35c22cb5,0xbb0ebbf6,0xbb77bbfa,0x3ba83a2f,0x3a8a38ec,0xb4a5b913,0xb89bba4f,0x3b0e3bf6,0x3bff3b99,0x378b2e46,0xa648b505,
0x34a53913,0x3ac23bb6,0x3ba83a2f,0x38483444,0x33c62a48,0x2fd62648,0xbbc3bbfe,0xbbf1bbff,0x38c436d7,0x35053303,0xba6dbb3b,0xbb99bbce,
0x3add39ed,0x37e3367c,0xb81db95f,0xbaf6bb50,0x3bea3b88,0x393a389b,0xb0b2b564,0xba0fba8a,0x3c003c00,0xbbf1bbff,0,0x2fd62648,
0x3c003c00,0xbb99bbce,0,0x35053303,0x3c003c00,0xbaf6bb50,0,0x37e3367c,0x3c003c00,0xba0fba8a,0,0x393a389b,
0x3bc33bfe,0xbb77bbfa,0xb3c6aa48,0x35c22cb5,0x3a6d3b3b,0xb89bba4f,0xb8c4b6d7,0x3a8a38ec,0x381d395f,0xa648b505,0xbaddb9ed,0x3bff3b99,
0x30b23564,0x38483444,0xbbeabb88,0x3ac23bb6,0x3b0e3bf6,0xba8abbf1,0xb78bae46,0x389b2fd6,0x34a53913,0x2648b732,0xbba8ba2f,0x3bff3b25,
0xb78bae46,0x3ac237e3,0xbb0ebbf6,0x38483af6,0xbba8ba2f,0x3b503bfa,0xb4a5b913,0xb67c2cb5,0x39ed3bea,0xb93abbe2,0xb95fb0b2,0x3a0f3179,
0xb56433c6,0x38eca648,0xbb88bbc3,0x3a4f3bff,0xbbfeba6d,0x3b253bce,0xaa48b8c4,0xb7323303,0xb6d7badd,0xb444367c,0x3b3b381d,0xbbb6bb50,
0x38723bd9,0xb732bbce,0xbaa7b23e,0x3b253303,0xbaa7b23e,0x3bb6367c,0xb872bbd9,0x34443b50,0xb872bbd9,0x2cb53a8a,0x3aa7323e,0xbbfab89b,
0x3aa7323e,0xbbf1b9cb,0x38723bd9,0x2fd6b984,0x35643bc3,0xb303bbb6,0xbb88b3c6,0x3bce3444,0xbbfeb8c4,0x3b773a0f,0x2a48ba6d,0xb5c2393a,
0x36d7b81d,0xba8a2fd6,0x3b3b3add,0xb89bbbf1,0x395f3bea,0xa648bb25,0xb9ed30b2,0x3bff3732,0x2e463ba8,0x2648bb99,0xbbf6b4a5,0x3bff3505,
0xba2fbb0e,0x38483bb6,0x3913b78b,0xbac23444,0x3bf634a5,0xbb50b93a,0x2e463ba8,0x367cba0f,0xb913378b,0x3be22fd6,0xba2fbb0e,0x31793bf1,
0xb0b23b88,0x3444bb77,0xbbeab564,0x3bb635c2,0xb3c6bbfe,0xacb53be2,0x3bc3aa48,0xbbfab179,0x38c43b3b,0xafd6bbff,0xba6d36d7,0x3bf1a648,
0xbaddb95f,0x35053bce,0x381db9ed,0xbb993303,0xb61f3b64,0x37e3bb50,0xbb64b61f,0x3af6367c,0x361fbb64,0xb93a3a8a,0x3b64361f,0xba0fb89b,
0xb61f3b64,0x3a4fb984,0xbb64b61f,0x38ec39cb,0x361fbb64,0xbb253848,0x3b64361f,0xb732bac2,0xb8c43b3b,0x3984bb25,0xba6db6d7,0x39cb3732,
0x3addb95f,0xbbce37e3,0x381d39ed,0xb303baf6,0xbbea3564,0x3b772cb5,0xb0b2bb88,0xb5c23bfa,0x3bc32a48,0xb89bb8ec,0xb3c63bfe,0x3a8aba4f,
0xba2f3b0e,0x3ac2baf6,0xb913b78b,0x384837e3,0x3bf6b4a5,0xbb502cb5,0xae463ba8,0x367cbbfa,0xb913b78b,0x31793a4f,0x3a2fbb0e,0xbbe238ec,
0xae463ba8,0x39cbbb99,0xbbf634a5,0x39843505,0xbb3b3add,0x3b99bac2,0xb6d7b81d,0x35053848,0x39ed30b2,0xb7e3b5c2,0xb95f3bea,0x3af6bb77,
0x3564bbc3,0xba0f3be2,0x3b88b3c6,0xb93ab179,0xbbfe38c4,0x3a4fa648,0xaa48ba6d,0xb8ec3bff,0xbbd93aa7,0x3bfaba8a,0xb23eb872,0x2cb5389b,
0x323e3872,0x2fd6b9cb,0xbbd93aa7,0x3bf1b984,0x3bd9baa7,0xbb993848,0x323e3872,0x3505bac2,0xb23eb872,0xb7e33b77,0x3bd9baa7,0xbaf635c2,
0xbbfe3a6d,0x3be2ba4f,0x2a48b8c4,0xb17938ec,0xb6d73add,0x3984bb99,0xbb3b381d,0x39cbb505,0x395fb0b2,0xb303b444,0xb9ed3bea,0x3bcebbb6,
0x3b88bbc3,0xbb77393a,0x356433c6,0x35c2ba0f,0xbba83a2f,0x3b50ba0f,0x34a5b913,0xb67c393a,0xbb0e3bf6,0x3be2bbf1,0xb78b2e46,0x31792fd6,
0xb4a53913,0x39cbbb25,0xbba83a2f,0x3984b732,0x378bae46,0x3303b7e3,0xbb0e3bf6,0x3bcebaf6,0xbadd39ed,0x3a4fb9cb,0x381db95f,0xb8ec3984,
0xbbea3b88,0x3b25bac2,0x30b2b564,0xb7323848,0xbbc33bfe,0x3bb6bb77,0xb3c62a48,0xb44435c2,0xba6d3b3b,0x3bfabbe2,0xb8c436d7,0xacb53179,
0xb9a839a8,0x38ecb984,0x39a8b9a8,0xba4f39cb,0xb9a839a8,0x3732b848,0x39a8b9a8,0xbb253ac2,0xb9a839a8,0x3444b5c2,0x39a8b9a8,0xbbb63b77,
0xb9a839a8,0x2cb5b179,0x39a8b9a8,0xbbfa3be2,0xb81d395f,0x367cb93a,0x3addb9ed,0xbb503a0f,0xb0b23564,0xb179afd6,0x3beabb88,0xbbe23bf1,
0x33c6aa48,0xb9843732,0x3bc3bbfe,0xb9cb3b25,0x38c4b6d7,0xbbce3af6,0x3a6dbb3b,0xb30337e3,0xb4a53913,0x3179b8ec,0x3ba8ba2f,0xbbe23a4f,
0x378bae46,0xb9cb3505,0x3b0ebbf6,0xb9843b99,0x3ba8ba2f,0xbbce3bb6,0x34a5b913,0x33033444,0x3b0ebbf6,0xb5c23a0f,0xb78b2e46,0x3b77b93a,
0xaa4838c4,0xacb5b89b,0x3bfeba6d,0xbbfa3a8a,0x3b3bb81d,0xbbf13984,0x36d7badd,0xafd639cb,0x39edbbea,0xb5053ac2,0xb95f30b2,0x3b99b848,
0xb564b3c6,0x3af6b5c2,0xbb883bc3,0x37e3bb77,0x323e3872,0xb505b848,0x3bd9baa7,0xbb993ac2,0x3bd9baa7,0xbaf63b77,0xb23eb872,0x37e335c2,
0xb23eb872,0x393a3179,0xbbd93aa7,0x3a0fbbe2,0xbbd93aa7,0x38ecbbff,0x323e3872,0xba4f2648,0x36d7381d,0xb848b7e3,0x3b3bbadd,0xbac23af6,
0x395fbbea,0xb67c3bfa,0xb9edb0b2,0x3b50acb5,0xbb8833c6,0x3be2b8ec,0xb5643bc3,0xb179ba4f,0x2a483a6d,0xb984b505,0x3bfeb8c4,0xb9cb3b99,
0x3913378b,0xb9cbb732,0x3a2fbb0e,0xb9843b25,0x2e46bba8,0x33033af6,0xbbf634a5,0x3bceb7e3,0xba2f3b0e,0x35c2bbfa,0x3913378b,0xbb77acb5,
0x3bf6b4a5,0xba8a3a4f,0x2e46bba8,0x389b38ec,0x3a6d36d7,0xbaf6b67c,0x38c4bb3b,0xb7e33b50,0xb81db9ed,0x3a0f389b,0xbadd395f,0x393aba8a,
0x30b23b88,0xb8ecb9cb,0x3beab564,0xba4f3984,0x33c6bbfe,0x37323ac2,0xbbc3aa48,0x3b25b848,0x3b64361f,0xbbb6b5c2,0x361fbb64,0xb4443b77,
0xbb64b61f,0x3bfa3179,0xb61f3b64,0x2cb5bbe2,0x3b64361f,0xbbf12648,0x361fbb64,0x2fd63bff,0xbb64b61f,0x3b99b303,0xb61f3b64,0xb505bbce,
0x3bea3564,0xbbffb505,0x30b2bb88,0xa6483b99,0xbbc32a48,0x3ac2b444,0x33c63bfe,0xb848bbb6,0x3a6db6d7,0xb67c3a0f,0xb8c4bb3b,0x3b50393a,
0xb81d39ed,0xb179bbf1,0x3add395f,0xbbe2afd6,0x3bf634a5,0xbbceb444,0xae46bba8,0x33033bb6,0xb913378b,0x35c2b93a,0x3a2f3b0e,0xbb77ba0f,
0xae46bba8,0x389b3bf1,0xbbf6b4a5,0x3a8aafd6,0x3a2f3b0e,0xbbffb732,0x3913b78b,0x26483b25,0x3b8833c6,0xbb25b303,0xb564bbc3,0x37323bce,
0xaa483a6d,0xb444bb50,0x3bfe38c4,0xbbb6b67c,0xbb3bbadd,0x3bfa389b,0xb6d7381d,0xacb5ba8a,0x39edb0b2,0xafd63984,0xb95fbbea,0x3bf139cb,
0x3aa7323e,0xba0fb179,0xb872bbd9,0x393a3be2,0x38723bd9,0xba4fbbff,0x3aa7323e,0xb8ec2648,0xbaa7b23e,0x3732b303,0x38723bd9,0xbb25bbce,
0xb872bbd9,0x3bb63b50,0xbaa7b23e,0x3444b67c,0x395f30b2,0xb89bafd6,0xb9edbbea,0x3a8a3bf1,0x3b883bc3,0xbbffbb25,0x3564b3c6,0xa6483732,
0x2a4838c4,0xb848baf6,0x3bfe3a6d,0xbac2b7e3,0xbb3bb81d,0x367cacb5,0x36d73add,0xbb50bbfa,0x378b2e46,0xb5c2acb5,0xbb0ebbf6,0x3b773bfa,
0x3ba83a2f,0xba8ab8ec,0xb4a5b913,0x389b3a4f,0x3b0e3bf6,0xbbffbb99,0x378b2e46,0x26483505,0x34a53913,0xbac2bbb6,0x3ba83a2f,0xb848b444,
0x33c62a48,0xafd6a648,0xbbc3bbfe,0x3bf13bff,0x38c436d7,0xb505b303,0xba6dbb3b,0x3b993bce,0x3add39ed,0xb7e3b67c,0xb81db95f,0x3af63b50,
0x3bea3b88,0xb93ab89b,0xb0b2b564,0x3a0f3a8a,0x3c003c00,0x38ec3984,0,0xba4fb9cb,0x3c003c00,0x37323848,0,0xbb25bac2,
0x3c003c00,0x344435c2,0,0xbbb6bb77,0x3c003c00,0x2cb53179,0,0xbbfabbe2,0xb3c6aa48,0xbb50ba0f,0xbbc3bbfe,0xb67cb93a,
0xb8c4b6d7,0xbbe2bbf1,0xba6dbb3b,0x3179afd6,0xbaddb9ed,0xb9cbbb25,0xb81db95f,0x39843732,0xbbeabb88,0xb303b7e3,0xb0b2b564,0x3bce3af6,
0xbb0ebbf6,0xb179b8ec,0x378b2e46,0x3be23a4f,0xb4a5b913,0x39cb3505,0x3ba83a2f,0x39843b99,0x378b2e46,0x3bce3bb6,0x3b0e3bf6,0xb3033444,
0x3ba83a2f,0x35c23a0f,0x34a53913,0xbb77b93a,0x395f30b2,0x3bfa3a8a,0x39ed3bea,0xacb5389b,0x3b883bc3,0x2fd639cb,0xb56433c6,0xbbf1b984,
0x2a4838c4,0xbb99b848,0xbbfeba6d,0xb505bac2,0xbb3bb81d,0xb7e3bb77,0xb6d7badd,0x3af635c2,0x38723bd9,0xb5053848,0xbaa7b23e,0xbb99bac2,
0xbaa7b23e,0xbaf6bb77,0xb872bbd9,0x37e3b5c2,0xb872bbd9,0x393ab179,0x3aa7323e,0x3a0f3be2,0x3aa7323e,0x38ec3bff,0x38723bd9,0xba4fa648,
0xbb88b3c6,0xbac2baf6,0xb564bbc3,0x3848b7e3,0x2a48ba6d,0x3b502cb5,0x3bfe38c4,0x367c3bfa,0x3b3b3add,0xb1793a4f,0xb6d7381d,0xbbe2b8ec,
0xb9ed30b2,0xb9cbbb99,0xb95fbbea,0x3984b505,0xae46bba8,0x39cbb732,0x3bf634a5,0x39843b25,0x3a2f3b0e,0xb3033af6,0xb913378b,0xbbceb7e3,
0xbbf6b4a5,0xb5c2bbfa,0xae46bba8,0x3b77acb5,0x3913b78b,0x3a8a3a4f,0x3a2f3b0e,0xb89b38ec,0x3bea3564,0x37e33b50,0xb0b23b88,0xbaf6367c,
0xbbc32a48,0xb93aba8a,0xb3c6bbfe,0x3a0fb89b,0x3a6db6d7,0x3a4f3984,0x38c43b3b,0xb8ec39cb,0xb81d39ed,0xbb25b848,0xbaddb95f,0x3732bac2,
0xb61f3b64,0xbbb635c2,0xbb64b61f,0xb444bb77,0x361fbb64,0x3bfab179,0x3b64361f,0x2cb53be2,0xb61f3b64,0xbbf1a648,0xbb64b61f,0x2fd6bbff,
0x361fbb64,0x3b993303,0x3b64361f,0xb5053bce,0xba6db6d7,0xa648bb99,0x38c4bb3b,0x3bffb505,0x381d39ed,0xb8483bb6,0xbadd395f,0xbac2b444,
0xb0b2bb88,0x3b50b93a,0x3beab564,0x367c3a0f,0xb3c63bfe,0xbbe22fd6,0xbbc3aa48,0x3179bbf1,0x3a2fbb0e,0x3bceb444,0x3913378b,0xb3033bb6,
0xbbf634a5,0xb5c2b93a,0x2e46bba8,0x3b77ba0f,0x3913378b,0xb89b3bf1,0xba2f3b0e,0xba8aafd6,0x2e46bba8,0x3bffb732,0x3bf6b4a5,0xa6483b25,
0x36d7381d,0xb7323bce,0xbb3b3add,0xbb253303,0x395fbbea,0x3bb6b67c,0x39ed30b2,0xb4443b50,0xbb8833c6,0x2cb5ba8a,0x3564bbc3,0x3bfab89b,
0x2a483a6d,0xbbf139cb,0xbbfe38c4,0xafd6b984,0xbbd93aa7,0xba0f3179,0xb23eb872,0x393abbe2,0x323e3872,0xba4f3bff,0xbbd93aa7,0xb8eca648,
0x3bd9baa7,0x37323303,0x323e3872,0xbb253bce,0xb23eb872,0x3bb6bb50,0x3bd9baa7,0x3444367c,0x2a48b8c4,0x3a8abbf1,0x3bfeba6d,0x389bafd6,
0xbb3b381d,0xa648b732,0x36d7badd,0x3bffbb25,0xb9ed3bea,0xbac237e3,0xb95f30b2,0x3848baf6,0x356433c6,0xbb503bfa,0xbb883bc3,0xb67cacb5,
0x3ba8ba2f,0x35c2acb5,0xb4a53913,0xbb773bfa,0x3b0ebbf6,0x3a8ab8ec,0x378bae46,0xb89b3a4f,0x34a5b913,0x3bffbb99,0x3ba8ba2f,0xa6483505,
0xb78b2e46,0x3ac2bbb6,0x3b0ebbf6,0x3848b444,0xb81d395f,0xbbf13bff,0xbadd39ed,0xafd62648,0xb0b23564,0xbb993bce,0xbbea3b88,0xb5053303,
0x33c6aa48,0xbaf63b50,0xbbc33bfe,0xb7e3367c,0x38c4b6d7,0xba0f3a8a,0xba6d3b3b,0xb93a389b,0xb9a839a8,0x2fd6a648,0x39a8b9a8,0x3bf1bbff,
0xb9a839a8,0x3505b303,0x39a8b9a8,0x3b99bbce,0xb9a839a8,0x37e3b67c,0x39a8b9a8,0x3af6bb50,0xb9a839a8,0x393ab89b,0x39a8b9a8,0x3a0fba8a,
0x3addb9ed,0x3b77bbfa,0x381db95f,0xb5c22cb5,0x3beabb88,0x389bba4f,0x30b2b564,0xba8a38ec,0x3bc3bbfe,0x2648b505,0xb3c62a48,0xbbff3b99,
0x3a6dbb3b,0xb8483444,0xb8c436d7,0xbac23bb6,0x34a5b913,0xb89b2fd6,0xbba83a2f,0xba8a3bf1,0xb78b2e46,0xbbff3b25,0xbb0e3bf6,0x26483732,
0xbba83a2f,0xb8483af6,0xb4a53913,0x3ac2b7e3,0xbb0e3bf6,0x367c2cb5,0x378bae46,0x3b50bbfa,0xbbfe3a6d,0xb93a3be2,0xaa4838c4,0x3a0fb179,
0xb6d73add,0x38ec2648,0x3b3bb81d,0x3a4fbbff,0x395fb0b2,0x3b25bbce,0x39edbbea,0xb732b303,0x3b88bbc3,0xb444b67c,0xb564b3c6,0xbbb63b50,
0x323e3872,0x3b25b303,0x3bd9baa7,0x3732bbce,0x3bd9baa7,0x3444bb50,0xb23eb872,0xbbb6367c,0xb23eb872,0xbbfa389b,0xbbd93aa7,0xacb53a8a,
0xbbd93aa7,0x2fd63984,0x323e3872,0x3bf1b9cb,0x3b3bbadd,0x3303bbb6,0xb6d7b81d,0xbbce3444,0xb9edb0b2,0xbb773a0f,0xb95f3bea,0x35c2393a,
0xb5643bc3,0x3a8a2fd6,0x3b88b3c6,0x389bbbf1,0x3bfeb8c4,0x2648bb25,0xaa48ba6d,0xbbff3732,0xb913b78b,0xbbff3505,0xba2f3b0e,0x26483b99,
0xae463ba8,0x3ac23444,0x3bf6b4a5,0x3848bbb6,0x3a2fbb0e,0xb67cba0f,0xb913b78b,0xbb50393a,0xbbf634a5,0xb1793bf1,0xae463ba8,0x3be2afd6,
0xb8c43b3b,0x34443b77,0x3a6d36d7,0x3bb6b5c2,0x3addb95f,0xacb5bbe2,0xb81db9ed,0xbbfa3179,0xbbea3564,0xafd63bff,0x30b23b88,0x3bf12648,
0x3bc32a48,0x3505bbce,0x33c6bbfe,0xbb99b303,0x3b64361f,0x3af6b67c,0x361fbb64,0xb7e3bb50,0xbb64b61f,0xba0f389b,0xb61f3b64,0x393a3a8a,
0x3b64361f,0x38ecb9cb,0x361fbb64,0xba4fb984,0xbb64b61f,0xb7323ac2,0xb61f3b64,0x3b253848,0x30b2bb88,0xb984bb25,0xbbeab564,0xb9cb3732,
0x33c63bfe,0x3bce37e3,0x3bc3aa48,0x3303baf6,0xb8c4bb3b,0xbb772cb5,0xba6d36d7,0x35c23bfa,0x3add395f,0x389bb8ec,0x381db9ed,0xba8aba4f,
0xbbf6b4a5,0xb84837e3,0x2e463ba8,0x3ac23af6,0x3913b78b,0xb67cbbfa,0xba2fbb0e,0xbb50acb5,0x2e463ba8,0x3be238ec,0x3bf634a5,0x3179ba4f,
0xba2fbb0e,0xb9843505,0xb913378b,0x39cb3b99,0x35643bc3,0x3b993ac2,0x3b8833c6,0x3505b848,0xbbfeb8c4,0xb7e335c2,0xaa483a6d,0x3af63b77,
0x36d7b81d,0xba0fbbe2,0xbb3bbadd,0xb93a3179,0x395f3bea,0x3a4f2648,0x39edb0b2,0xb8ecbbff,0x3aa7323e,0x2cb5b89b,0xb872bbd9,0xbbfaba8a,
0x38723bd9,0x3bf13984,0x3aa7323e,0xafd6b9cb,0xbaa7b23e,0x35053ac2,0x38723bd9,0x3b993848,0xb872bbd9,0xbaf6b5c2,0xbaa7b23e,0x37e33b77,
0xb9edbbea,0xbbe2ba4f,0xb95fb0b2,0x317938ec,0x3564b3c6,0xb984bb99,0xbb88bbc3,0xb9cbb505,0x3bfe3a6d,0x3303b444,0xaa48b8c4,0xbbcebbb6,
0x36d73add,0x3b77393a,0x3b3b381d,0xb5c2ba0f,0xb78bae46,0x367c393a,0x3b0e3bf6,0x3b503a0f,0xbba8ba2f,0xb1792fd6,0x34a53913,0x3be23bf1,
0xbb0ebbf6,0xb984b732,0xb78bae46,0x39cb3b25,0xb4a5b913,0xbbcebaf6,0xbba8ba2f,0x330337e3,0x3bc33bfe,0x3a4f39cb,0x33c62a48,0xb8ecb984,
0x3a6d3b3b,0x3b253ac2,0x38c436d7,0xb732b848,0x381d395f,0x3bb63b77,0x3add39ed,0xb444b5c2,0x30b23564,0x3bfa3be2,0x3bea3b88,0xacb5b179,
0x3c003c00,0xb8ecb984,0,0x3a4f39cb,0x3c003c00,0xb732b848,0,0x3b253ac2,0x3c003c00,0xb444b5c2,0,0x3bb63b77,
0x3c003c00,0xacb5b179,0,0x3bfa3be2,0xb3c6aa48,0x3b503a0f,0xbbc3bbfe,0x367c393a,0xb8c4b6d7,0x3be23bf1,0xba6dbb3b,0xb1792fd6,
0xbaddb9ed,0x39cb3b25,0xb81db95f,0xb984b732,0xbbeabb88,0x330337e3,0xb0b2b564,0xbbcebaf6,0xbb0ebbf6,0x317938ec,0x378b2e46,0xbbe2ba4f,
0xb4a5b913,0xb9cbb505,0x3ba83a2f,0xb984bb99,0x378b2e46,0xbbcebbb6,0x3b0e3bf6,0x3303b444,0x3ba83a2f,0xb5c2ba0f,0x34a53913,0x3b77393a,
0x395f30b2,0xbbfaba8a,0x39ed3bea,0x2cb5b89b,0x3b883bc3,0xafd6b9cb,0xb56433c6,0x3bf13984,0x2a4838c4,0x3b993848,0xbbfeba6d,0x35053ac2,
0xbb3bb81d,0x37e33b77,0xb6d7badd,0xbaf6b5c2,0x38723bd9,0x3505b848,0xbaa7b23e,0x3b993ac2,0xbaa7b23e,0x3af63b77,0xb872bbd9,0xb7e335c2,
0xb872bbd9,0xb93a3179,0x3aa7323e,0xba0fbbe2,0x3aa7323e,0xb8ecbbff,0x38723bd9,0x3a4f2648,0xbb88b3c6,0x3ac23af6,0xb564bbc3,0xb84837e3,
0x2a48ba6d,0xbb50acb5,0x3bfe38c4,0xb67cbbfa,0x3b3b3add,0x3179ba4f,0xb6d7381d,0x3be238ec,0xb9ed30b2,0x39cb3b99,0xb95fbbea,0xb9843505,
0xae46bba8,0xb9cb3732,0x3bf634a5,0xb984bb25,0x3a2f3b0e,0x3303baf6,0xb913378b,0x3bce37e3,0xbbf6b4a5,0x35c23bfa,0xae46bba8,0xbb772cb5,
0x3913b78b,0xba8aba4f,0x3a2f3b0e,0x389bb8ec,0x3bea3564,0xb7e3bb50,0xb0b23b88,0x3af6b67c,0xbbc32a48,0x393a3a8a,0xb3c6bbfe,0xba0f389b,
0x3a6db6d7,0xba4fb984,0x38c43b3b,0x38ecb9cb,0xb81d39ed,0x3b253848,0xbaddb95f,0xb7323ac2,0xb61f3b64,0x3bb6b5c2,0xbb64b61f,0x34443b77,
0x361fbb64,0xbbfa3179,0x3b64361f,0xacb5bbe2,0xb61f3b64,0x3bf12648,0xbb64b61f,0xafd63bff,0x361fbb64,0xbb99b303,0x3b64361f,0x3505bbce,
0xba6db6d7,0x26483b99,0x38c4bb3b,0xbbff3505,0x381d39ed,0x3848bbb6,0xbadd395f,0x3ac23444,0xb0b2bb88,0xbb50393a,0x3beab564,0xb67cba0f,
0xb3c63bfe,0x3be2afd6,0xbbc3aa48,0xb1793bf1,0x3a2fbb0e,0xbbce3444,0x3913378b,0x3303bbb6,0xbbf634a5,0x35c2393a,0x2e46bba8,0xbb773a0f,
0x3913378b,0x389bbbf1,0xba2f3b0e,0x3a8a2fd6,0x2e46bba8,0xbbff3732,0x3bf6b4a5,0x2648bb25,0x36d7381d,0x3732bbce,0xbb3b3add,0x3b25b303,
0x395fbbea,0xbbb6367c,0x39ed30b2,0x3444bb50,0xbb8833c6,0xacb53a8a,0x3564bbc3,0xbbfa389b,0x2a483a6d,0x3bf1b9cb,0xbbfe38c4,0x2fd63984,
0xbbd93aa7,0x3a0fb179,0xb23eb872,0xb93a3be2,0x323e3872,0x3a4fbbff,0xbbd93aa7,0x38ec2648,0x3bd9baa7,0xb732b303,0x323e3872,0x3b25bbce,
0xb23eb872,0xbbb63b50,0x3bd9baa7,0xb444b67c,0x2a48b8c4,0xba8a3bf1,0x3bfeba6d,0xb89b2fd6,0xbb3b381d,0x26483732,0x36d7badd,0xbbff3b25,
0xb9ed3bea,0x3ac2b7e3,0xb95f30b2,0xb8483af6,0x356433c6,0x3b50bbfa,0xbb883bc3,0x367c2cb5,0x3ba8ba2f,0xb5c22cb5,0xb4a53913,0x3b77bbfa,
0x3b0ebbf6,0xba8a38ec,0x378bae46,0x389bba4f,0x34a5b913,0xbbff3b99,0x3ba8ba2f,0x2648b505,0xb78b2e46,0xbac23bb6,0x3b0ebbf6,0xb8483444,
0xb81d395f,0x3bf1bbff,0xbadd39ed,0x2fd6a648,0xb0b23564,0x3b99bbce,0xbbea3b88,0x3505b303,0x33c6aa48,0x3af6bb50,0xbbc33bfe,0x37e3b67c,
0x38c4b6d7,0x3a0fba8a,0xba6d3b3b,0x393ab89b,0xb9a839a8,0xafd62648,0x39a8b9a8,0xbbf13bff,0xb9a839a8,0xb5053303,0x39a8b9a8,0xbb993bce,
0xb9a839a8,0xb7e3367c,0x39a8b9a8,0xbaf63b50,0xb9a839a8,0xb93a389b,0x39a8b9a8,0xba0f3a8a,0x3addb9ed,0xbb773bfa,0x381db95f,0x35c2acb5,
0x3beabb88,0xb89b3a4f,0x30b2b564,0x3a8ab8ec,0x3bc3bbfe,0xa6483505,0xb3c62a48,0x3bffbb99,0x3a6dbb3b,0x3848b444,0xb8c436d7,0x3ac2bbb6,
0x34a5b913,0x389bafd6,0xbba83a2f,0x3a8abbf1,0xb78b2e46,0x3bffbb25,0xbb0e3bf6,0xa648b732,0xbba83a2f,0x3848baf6,0xb4a53913,0xbac237e3,
0xbb0e3bf6,0xb67cacb5,0x378bae46,0xbb503bfa,0xbbfe3a6d,0x393abbe2,0xaa4838c4,0xba0f3179,0xb6d73add,0xb8eca648,0x3b3bb81d,0xba4f3bff,
0x395fb0b2,0xbb253bce,0x39edbbea,0x37323303,0x3b88bbc3,0x3444367c,0xb564b3c6,0x3bb6bb50,0x323e3872,0xbb253303,0x3bd9baa7,0xb7323bce,
0x3bd9baa7,0xb4443b50,0xb23eb872,0x3bb6b67c,0xb23eb872,0x3bfab89b,0xbbd93aa7,0x2cb5ba8a,0xbbd93aa7,0xafd6b984,0x323e3872,0xbbf139cb,
0x3b3bbadd,0xb3033bb6,0xb6d7b81d,0x3bceb444,0xb9edb0b2,0x3b77ba0f,0xb95f3bea,0xb5c2b93a,0xb5643bc3,0xba8aafd6,0x3b88b3c6,0xb89b3bf1,
0x3bfeb8c4,0xa6483b25,0xaa48ba6d,0x3bffb732,0xb913b78b,0x3bffb505,0xba2f3b0e,0xa648bb99,0xae463ba8,0xbac2b444,0x3bf6b4a5,0xb8483bb6,
0x3a2fbb0e,0x367c3a0f,0xb913b78b,0x3b50b93a,0xbbf634a5,0x3179bbf1,0xae463ba8,0xbbe22fd6,0xb8c43b3b,0xb444bb77,0x3a6d36d7,0xbbb635c2,
0x3addb95f,0x2cb53be2,0xb81db9ed,0x3bfab179,0xbbea3564,0x2fd6bbff,0x30b23b88,0xbbf1a648,0x3bc32a48,0xb5053bce,0x33c6bbfe,0x3b993303,
0x3b64361f,0xbaf6367c,0x361fbb64,0x37e33b50,0xbb64b61f,0x3a0fb89b,0xb61f3b64,0xb93aba8a,0x3b64361f,0xb8ec39cb,0x361fbb64,0x3a4f3984,
0xbb64b61f,0x3732bac2,0xb61f3b64,0xbb25b848,0x30b2bb88,0x39843b25,0xbbeab564,0x39cbb732,0x33c63bfe,0xbbceb7e3,0x3bc3aa48,0xb3033af6,
0xb8c4bb3b,0x3b77acb5,0xba6d36d7,0xb5c2bbfa,0x3add395f,0xb89b38ec,0x381db9ed,0x3a8a3a4f,0xbbf6b4a5,0x3848b7e3,0x2e463ba8,0xbac2baf6,
0x3913b78b,0x367c3bfa,0xba2fbb0e,0x3b502cb5,0x2e463ba8,0xbbe2b8ec,0x3bf634a5,0xb1793a4f,0xba2fbb0e,0x3984b505,0xb913378b,0xb9cbbb99,
0x35643bc3,0xbb99bac2,0x3b8833c6,0xb5053848,0xbbfeb8c4,0x37e3b5c2,0xaa483a6d,0xbaf6bb77,0x36d7b81d,0x3a0f3be2,0xbb3bbadd,0x393ab179,
0x395f3bea,0xba4fa648,0x39edb0b2,0x38ec3bff,0x3aa7323e,0xacb5389b,0xb872bbd9,0x3bfa3a8a,0x38723bd9,0xbbf1b984,0x3aa7323e,0x2fd639cb,
0xbaa7b23e,0xb505bac2,0x38723bd9,0xbb99b848,0xb872bbd9,0x3af635c2,0xbaa7b23e,0xb7e3bb77,0xb9edbbea,0x3be23a4f,0xb95fb0b2,0xb179b8ec,
0x3564b3c6,0x39843b99,0xbb88bbc3,0x39cb3505,0x3bfe3a6d,0xb3033444,0xaa48b8c4,0x3bce3bb6,0x36d73add,0xbb77b93a,0x3b3b381d,0x35c23a0f,
0xb78bae46,0xb67cb93a,0x3b0e3bf6,0xbb50ba0f,0xbba8ba2f,0x3179afd6,0x34a53913,0xbbe2bbf1,0xbb0ebbf6,0x39843732,0xb78bae46,0xb9cbbb25,
0xb4a5b913,0x3bce3af6,0xbba8ba2f,0xb303b7e3,0x3bc33bfe,0xba4fb9cb,0x33c62a48,0x38ec3984,0x3a6d3b3b,0xbb25bac2,0x38c436d7,0x37323848,
0x381d395f,0xbbb6bb77,0x3add39ed,0x344435c2,0x30b23564,0xbbfabbe2,0x3bea3b88,0x2cb53179,0x3c003c00,0xafd6a648,0,0xbbf1bbff,
0x3c003c00,0xb505b303,0,0xbb99bbce,0x3c003c00,0xb7e3b67c,0,0xbaf6bb50,0x3c003c00,0xb93ab89b,0,0xba0fba8a,
0xbbc3bbfe,0x35c22cb5,0x33c62a48,0x3b773bfa,0xba6dbb3b,0x3a8a38ec,0x38c436d7,0x389b3a4f,0xb81db95f,0x3bff3b99,0x3add39ed,0x26483505,
0xb0b2b564,0x3ac23bb6,0x3bea3b88,0xb848b444,0x3b0e3bf6,0xb89bafd6,0xb78bae46,0xba8abbf1,0x34a53913,0xbbffbb25,0xbba8ba2f,0x2648b732,
0xb78bae46,0xb848baf6,0xbb0ebbf6,0x3ac237e3,0xbba8ba2f,0x367cacb5,0xb4a5b913,0x3b503bfa,0xb9edbbea,0x3a0f3179,0x395f30b2,0x393a3be2,
0x3564b3c6,0x3a4f3bff,0x3b883bc3,0xb8ec2648,0x3bfe3a6d,0xb7323303,0x2a4838c4,0xbb25bbce,0x36d73add,0xbbb6bb50,0xbb3bb81d,0x3444b67c,
0x38723bd9,0xbb25b303,0xbaa7b23e,0xb732bbce,0xbaa7b23e,0xb444bb50,0xb872bbd9,0x3bb6367c,0xb872bbd9,0x3bfa389b,0x3aa7323e,0x2cb53a8a,
0x3aa7323e,0xafd63984,0x38723bd9,0xbbf1b9cb,0xb564bbc3,0x3bce3444,0x3b8833c6,0x33033bb6,0x3bfe38c4,0xb5c2393a,0xaa483a6d,0xbb77ba0f,
0xb6d7381d,0xb89bbbf1,0xbb3bbadd,0x3a8aafd6,0xb95fbbea,0x3bff3732,0x39edb0b2,0x26483b25,0x2e463ba8,0xbbffb505,0xbbf6b4a5,0x2648bb99,
0xba2fbb0e,0x3ac2b444,0x3913b78b,0x38483bb6,0x3bf634a5,0xb67c3a0f,0x2e463ba8,0xbb50b93a,0xb913378b,0xb179bbf1,0xba2fbb0e,0x3be22fd6,
0x30b2bb88,0x3bb635c2,0x3bea3564,0xb4443b77,0x33c63bfe,0xbbfab179,0xbbc32a48,0x2cb5bbe2,0xb8c4bb3b,0x3bf1a648,0x3a6db6d7,0x2fd63bff,
0x3add395f,0xbb993303,0xb81d39ed,0xb505bbce,0xb61f3b64,0xbaf6b67c,0xbb64b61f,0x37e3bb50,0x361fbb64,0x3a0f389b,0x3b64361f,0xb93a3a8a,
0xb61f3b64,0xb8ecb9cb,0xbb64b61f,0x3a4fb984,0x361fbb64,0x37323ac2,0x3b64361f,0xbb253848,0x38c4bb3b,0x39cb3732,0x3a6d36d7,0xb9843b25,
0xbadd395f,0xb303baf6,0xb81db9ed,0x3bceb7e3,0x3beab564,0xb5c23bfa,0x30b23b88,0xbb77acb5,0xbbc3aa48,0x3a8aba4f,0x33c6bbfe,0x389b38ec,
0xba2f3b0e,0xb848b7e3,0xb913b78b,0x3ac2baf6,0x3bf6b4a5,0xb67c3bfa,0xae463ba8,0xbb502cb5,0xb913b78b,0x3be2b8ec,0x3a2fbb0e,0x31793a4f,
0xae463ba8,0xb984b505,0xbbf634a5,0x39cbbb99,0x3b3bbadd,0x35053848,0x36d7381d,0xbb993ac2,0xb9edb0b2,0x3af6bb77,0x395fbbea,0x37e335c2,
0xb5643bc3,0xb93ab179,0xbb8833c6,0x3a0fbbe2,0x3bfeb8c4,0xb8ec3bff,0x2a483a6d,0xba4f2648,0xbbd93aa7,0xacb5b89b,0xb23eb872,0x3bfaba8a,
0x323e3872,0xbbf13984,0xbbd93aa7,0x2fd6b9cb,0x3bd9baa7,0xb5053ac2,0x323e3872,0xbb993848,0xb23eb872,0x3af6b5c2,0x3bd9baa7,0xb7e33b77,
0x3bfeba6d,0xb17938ec,0xaa4838c4,0xbbe23a4f,0x36d7badd,0x39cbb505,0x3b3bb81d,0xb9843b99,0xb95f30b2,0x3bcebbb6,0x39edbbea,0x33033444,
0xbb883bc3,0x35c2ba0f,0xb564b3c6,0x3b77b93a,0xbba83a2f,0x367cb93a,0x34a5b913,0x3b50ba0f,0xbb0e3bf6,0xb179afd6,0xb78b2e46,0x3be2bbf1,
0xb4a53913,0xb9843732,0xbba83a2f,0x39cbbb25,0x378bae46,0xbbce3af6,0xbb0e3bf6,0x3303b7e3,0x3addb9ed,0xb8ec3984,0xb81d395f,0xba4f39cb,
0x3beabb88,0xb7323848,0xb0b23564,0xbb253ac2,0x3bc3bbfe,0xb44435c2,0x33c6aa48,0xbbb63b77,0x3a6dbb3b,0xacb53179,0x38c4b6d7,0xbbfa3be2,
0xb9a839a8,0x3a4fb9cb,0x39a8b9a8,0x38ecb984,0xb9a839a8,0x3b25bac2,0x39a8b9a8,0x3732b848,0xb9a839a8,0x3bb6bb77,0x39a8b9a8,0x3444b5c2,
0xb9a839a8,0x3bfabbe2,0x39a8b9a8,0x2cb5b179,0x381db95f,0xbb503a0f,0xbadd39ed,0xb67c393a,0x30b2b564,0xbbe23bf1,0xbbea3b88,0x31792fd6,
0xb3c62a48,0xb9cb3b25,0xbbc33bfe,0x3984b732,0xb8c436d7,0xb30337e3,0xba6d3b3b,0x3bcebaf6,0xb4a53913,0x3be2ba4f,0x3ba8ba2f,0x3179b8ec,
0x378bae46,0x3984bb99,0x3b0ebbf6,0xb9cb3505,0x3ba8ba2f,0xb303b444,0x34a5b913,0xbbce3bb6,0x3b0ebbf6,0xbb77393a,0xb78b2e46,0xb5c23a0f,
0x2a48b8c4,0xbbfa3a8a,0xbbfe3a6d,0x2cb5389b,0xbb3b381d,0xafd639cb,0xb6d73add,0x3bf1b984,0xb9ed3bea,0x3b99b848,0x395fb0b2,0x3505bac2,
0x356433c6,0x37e3bb77,0x3b88bbc3,0xbaf635c2,0x323e3872,0x3b99bac2,0x3bd9baa7,0xb505b848,0x3bd9baa7,0xb7e3b5c2,0xb23eb872,0xbaf63b77,
0xb23eb872,0xba0f3be2,0xbbd93aa7,0x393a3179,0xbbd93aa7,0x3a4fa648,0x323e3872,0x38ecbbff,0xb6d7b81d,0xbac23af6,0xbb3b3add,0x384837e3,
0xb95f3bea,0x3b50acb5,0x39ed30b2,0x367cbbfa,0x3b88b3c6,0xb179ba4f,0x3564bbc3,0xbbe238ec,0xaa48ba6d,0xb9cb3b99,0xbbfe38c4,0x39843505,
0x3913378b,0x3984bb25,0x3a2fbb0e,0xb9cbb732,0x2e46bba8,0xbbce37e3,0xbbf634a5,0x33033af6,0xba2f3b0e,0x3b772cb5,0x3913378b,0x35c2bbfa,
0x3bf6b4a5,0xb89bb8ec,0x2e46bba8,0xba8a3a4f,0xba6db6d7,0xb7e33b50,0xb8c43b3b,0x3af6367c,0x381d39ed,0x393aba8a,0x3addb95f,0xba0fb89b,
0xb0b2bb88,0xba4f3984,0xbbea3564,0x38ec39cb,0xb3c63bfe,0x3b25b848,0x3bc32a48,0xb732bac2,0x3b64361f,0x3444bb77,0x361fbb64,0xbbb6b5c2,
0xbb64b61f,0xacb53be2,0xb61f3b64,0x3bfa3179,0x3b64361f,0xafd6bbff,0x361fbb64,0xbbf12648,0xbb64b61f,0x35053bce,0xb61f3b64,0x3b99b303,
0xbbeab564,0xa6483b99,0xb0b23b88,0x3bff3505,0x3bc3aa48,0xb848bbb6,0xb3c6bbfe,0xbac23444,0xba6d36d7,0x3b50393a,0x38c43b3b,0x367cba0f,
0x381db9ed,0xbbe2afd6,0xbaddb95f,0x31793bf1,0x3bf634a5,0xb303bbb6,0xae46bba8,0xbbceb444,0xb913378b,0x3b773a0f,0x3a2f3b0e,0x35c2b93a,
0xae46bba8,0xba8a2fd6,0xbbf6b4a5,0x389b3bf1,0x3a2f3b0e,0xa648bb25,0x3913b78b,0xbbffb732,0xbb88b3c6,0x37323bce,0x35643bc3,0x3b253303,
0x2a48ba6d,0xbbb6b67c,0xbbfeb8c4,0x34443b50,0x3b3b3add,0xacb5ba8a,0x36d7b81d,0xbbfab89b,0xb9ed30b2,0x3bf139cb,0x395f3bea,0x2fd6b984,
0x3aa7323e,0xb93abbe2,0xb872bbd9,0xba0fb179,0x38723bd9,0x38eca648,0x3aa7323e,0xba4fbbff,0xbaa7b23e,0x3b253bce,0x38723bd9,0x3732b303,
0xb872bbd9,0xb444367c,0xbaa7b23e,0x3bb63b50,0xb95fb0b2,0x3a8a3bf1,0x39ed3bea,0x389b2fd6,0xbb88bbc3,0xa6483732,0xb56433c6,0x3bff3b25,
0xaa48b8c4,0xbac2b7e3,0xbbfeba6d,0x38483af6,0x3b3b381d,0xbb50bbfa,0xb6d7badd,0xb67c2cb5,0x378b2e46,0xbb77bbfa,0xbb0ebbf6,0xb5c2acb5,
0x3ba83a2f,0xb89bba4f,0xb4a5b913,0xba8ab8ec,0x3b0e3bf6,0xa648b505,0x378b2e46,0xbbffbb99,0x34a53913,0x38483444,0x3ba83a2f,0xbac2bbb6,
0xb3c6aa48,0x3bf13bff,0x3bc33bfe,0x2fd62648,0xb8c4b6d7,0x3b993bce,0x3a6d3b3b,0x35053303,0xbaddb9ed,0x3af63b50,0x381d395f,0x37e3367c,
0xbbeabb88,0x3a0f3a8a,0x30b23564,0x393a389b,0x3c003c00,0x2fd62648,0,0x3bf13bff,0x3c003c00,0x35053303,0,0x3b993bce,
0x3c003c00,0x37e3367c,0,0x3af63b50,0x3c003c00,0x393a389b,0,0x3a0f3a8a,0xbbc3bbfe,0xb5c2acb5,0x33c62a48,0xbb77bbfa,
0xba6dbb3b,0xba8ab8ec,0x38c436d7,0xb89bba4f,0xb81db95f,0xbbffbb99,0x3add39ed,0xa648b505,0xb0b2b564,0xbac2bbb6,0x3bea3b88,0x38483444,
0x3b0e3bf6,0x389b2fd6,0xb78bae46,0x3a8a3bf1,0x34a53913,0x3bff3b25,0xbba8ba2f,0xa6483732,0xb78bae46,0x38483af6,0xbb0ebbf6,0xbac2b7e3,
0xbba8ba2f,0xb67c2cb5,0xb4a5b913,0xbb50bbfa,0xb9edbbea,0xba0fb179,0x395f30b2,0xb93abbe2,0x3564b3c6,0xba4fbbff,0x3b883bc3,0x38eca648,
0x3bfe3a6d,0x3732b303,0x2a4838c4,0x3b253bce,0x36d73add,0x3bb63b50,0xbb3bb81d,0xb444367c,0x38723bd9,0x3b253303,0xbaa7b23e,0x37323bce,
0xbaa7b23e,0x34443b50,0xb872bbd9,0xbbb6b67c,0xb872bbd9,0xbbfab89b,0x3aa7323e,0xacb5ba8a,0x3aa7323e,0x2fd6b984,0x38723bd9,0x3bf139cb,
0xb564bbc3,0xbbceb444,0x3b8833c6,0xb303bbb6,0x3bfe38c4,0x35c2b93a,0xaa483a6d,0x3b773a0f,0xb6d7381d,0x389b3bf1,0xbb3bbadd,0xba8a2fd6,
0xb95fbbea,0xbbffb732,0x39edb0b2,0xa648bb25,0x2e463ba8,0x3bff3505,0xbbf6b4a5,0xa6483b99,0xba2fbb0e,0xbac23444,0x3913b78b,0xb848bbb6,
0x3bf634a5,0x367cba0f,0x2e463ba8,0x3b50393a,0xb913378b,0x31793bf1,0xba2fbb0e,0xbbe2afd6,0x30b2bb88,0xbbb6b5c2,0x3bea3564,0x3444bb77,
0x33c63bfe,0x3bfa3179,0xbbc32a48,0xacb53be2,0xb8c4bb3b,0xbbf12648,0x3a6db6d7,0xafd6bbff,0x3add395f,0x3b99b303,0xb81d39ed,0x35053bce,
0xb61f3b64,0x3af6367c,0xbb64b61f,0xb7e33b50,0x361fbb64,0xba0fb89b,0x3b64361f,0x393aba8a,0xb61f3b64,0x38ec39cb,0xbb64b61f,0xba4f3984,
0x361fbb64,0xb732bac2,0x3b64361f,0x3b25b848,0x38c4bb3b,0xb9cbb732,0x3a6d36d7,0x3984bb25,0xbadd395f,0x33033af6,0xb81db9ed,0xbbce37e3,
0x3beab564,0x35c2bbfa,0x30b23b88,0x3b772cb5,0xbbc3aa48,0xba8a3a4f,0x33c6bbfe,0xb89bb8ec,0xba2f3b0e,0x384837e3,0xb913b78b,0xbac23af6,
0x3bf6b4a5,0x367cbbfa,0xae463ba8,0x3b50acb5,0xb913b78b,0xbbe238ec,0x3a2fbb0e,0xb179ba4f,0xae463ba8,0x39843505,0xbbf634a5,0xb9cb3b99,
0x3b3bbadd,0xb505b848,0x36d7381d,0x3b99bac2,0xb9edb0b2,0xbaf63b77,0x395fbbea,0xb7e3b5c2,0xb5643bc3,0x393a3179,0xbb8833c6,0xba0f3be2,
0x3bfeb8c4,0x38ecbbff,0x2a483a6d,0x3a4fa648,0xbbd93aa7,0x2cb5389b,0xb23eb872,0xbbfa3a8a,0x323e3872,0x3bf1b984,0xbbd93aa7,0xafd639cb,
0x3bd9baa7,0x3505bac2,0x323e3872,0x3b99b848,0xb23eb872,0xbaf635c2,0x3bd9baa7,0x37e3bb77,0x3bfeba6d,0x3179b8ec,0xaa4838c4,0x3be2ba4f,
0x36d7badd,0xb9cb3505,0x3b3bb81d,0x3984bb99,0xb95f30b2,0xbbce3bb6,0x39edbbea,0xb303b444,0xbb883bc3,0xb5c23a0f,0xb564b3c6,0xbb77393a,
0xbba83a2f,0xb67c393a,0x34a5b913,0xbb503a0f,0xbb0e3bf6,0x31792fd6,0xb78b2e46,0xbbe23bf1,0xb4a53913,0x3984b732,0xbba83a2f,0xb9cb3b25,
0x378bae46,0x3bcebaf6,0xbb0e3bf6,0xb30337e3,0x3addb9ed,0x38ecb984,0xb81d395f,0x3a4fb9cb,0x3beabb88,0x3732b848,0xb0b23564,0x3b25bac2,
0x3bc3bbfe,0x3444b5c2,0x33c6aa48,0x3bb6bb77,0x3a6dbb3b,0x2cb5b179,0x38c4b6d7,0x3bfabbe2,0xb9a839a8,0xba4f39cb,0x39a8b9a8,0xb8ec3984,
0xb9a839a8,0xbb253ac2,0x39a8b9a8,0xb7323848,0xb9a839a8,0xbbb63b77,0x39a8b9a8,0xb44435c2,0xb9a839a8,0xbbfa3be2,0x39a8b9a8,0xacb53179,
0x381db95f,0x3b50ba0f,0xbadd39ed,0x367cb93a,0x30b2b564,0x3be2bbf1,0xbbea3b88,0xb179afd6,0xb3c62a48,0x39cbbb25,0xbbc33bfe,0xb9843732,
0xb8c436d7,0x3303b7e3,0xba6d3b3b,0xbbce3af6,0xb4a53913,0xbbe23a4f,0x3ba8ba2f,0xb17938ec,0x378bae46,0xb9843b99,0x3b0ebbf6,0x39cbb505,
0x3ba8ba2f,0x33033444,0x34a5b913,0x3bcebbb6,0x3b0ebbf6,0x3b77b93a,0xb78b2e46,0x35c2ba0f,0x2a48b8c4,0x3bfaba8a,0xbbfe3a6d,0xacb5b89b,
0xbb3b381d,0x2fd6b9cb,0xb6d73add,0xbbf13984,0xb9ed3bea,0xbb993848,0x395fb0b2,0xb5053ac2,0x356433c6,0xb7e33b77,0x3b88bbc3,0x3af6b5c2,
0x323e3872,0xbb993ac2,0x3bd9baa7,0x35053848,0x3bd9baa7,0x37e335c2,0xb23eb872,0x3af6bb77,0xb23eb872,0x3a0fbbe2,0xbbd93aa7,0xb93ab179,
0xbbd93aa7,0xba4f2648,0x323e3872,0xb8ec3bff,0xb6d7b81d,0x3ac2baf6,0xbb3b3add,0xb848b7e3,0xb95f3bea,0xbb502cb5,0x39ed30b2,0xb67c3bfa,
0x3b88b3c6,0x31793a4f,0x3564bbc3,0x3be2b8ec,0xaa48ba6d,0x39cbbb99,0xbbfe38c4,0xb984b505,0x3913378b,0xb9843b25,0x3a2fbb0e,0x39cb3732,
0x2e46bba8,0x3bceb7e3,0xbbf634a5,0xb303baf6,0xba2f3b0e,0xbb77acb5,0x3913378b,0xb5c23bfa,0x3bf6b4a5,0x389b38ec,0x2e46bba8,0x3a8aba4f,
0xba6db6d7,0x37e3bb50,0xb8c43b3b,0xbaf6b67c,0x381d39ed,0xb93a3a8a,0x3addb95f,0x3a0f389b,0xb0b2bb88,0x3a4fb984,0xbbea3564,0xb8ecb9cb,
0xb3c63bfe,0xbb253848,0x3bc32a48,0x37323ac2,0x3b64361f,0xb4443b77,0x361fbb64,0x3bb635c2,0xbb64b61f,0x2cb5bbe2,0xb61f3b64,0xbbfab179,
0x3b64361f,0x2fd63bff,0x361fbb64,0x3bf1a648,0xbb64b61f,0xb505bbce,0xb61f3b64,0xbb993303,0xbbeab564,0x2648bb99,0xb0b23b88,0xbbffb505,
0x3bc3aa48,0x38483bb6,0xb3c6bbfe,0x3ac2b444,0xba6d36d7,0xbb50b93a,0x38c43b3b,0xb67c3a0f,0x381db9ed,0x3be22fd6,0xbaddb95f,0xb179bbf1,
0x3bf634a5,0x33033bb6,0xae46bba8,0x3bce3444,0xb913378b,0xbb77ba0f,0x3a2f3b0e,0xb5c2393a,0xae46bba8,0x3a8aafd6,0xbbf6b4a5,0xb89bbbf1,
0x3a2f3b0e,0x26483b25,0x3913b78b,0x3bff3732,0xbb88b3c6,0xb732bbce,0x35643bc3,0xbb25b303,0x2a48ba6d,0x3bb6367c,0xbbfeb8c4,0xb444bb50,
0x3b3b3add,0x2cb53a8a,0x36d7b81d,0x3bfa389b,0xb9ed30b2,0xbbf1b9cb,0x395f3bea,0xafd63984,0x3aa7323e,0x393a3be2,0xb872bbd9,0x3a0f3179,
0x38723bd9,0xb8ec2648,0x3aa7323e,0x3a4f3bff,0xbaa7b23e,0xbb25bbce,0x38723bd9,0xb7323303,0xb872bbd9,0x3444b67c,0xbaa7b23e,0xbbb6bb50,
0xb95fb0b2,0xba8abbf1,0x39ed3bea,0xb89bafd6,0xbb88bbc3,0x2648b732,0xb56433c6,0xbbffbb25,0xaa48b8c4,0x3ac237e3,0xbbfeba6d,0xb848baf6,
0x3b3b381d,0x3b503bfa,0xb6d7badd,0x367cacb5,0x378b2e46,0x3b773bfa,0xbb0ebbf6,0x35c22cb5,0x3ba83a2f,0x389b3a4f,0xb4a5b913,0x3a8a38ec,
0x3b0e3bf6,0x26483505,0x378b2e46,0x3bff3b99,0x34a53913,0xb848b444,0x3ba83a2f,0x3ac23bb6,0xb3c6aa48,0xbbf1bbff,0x3bc33bfe,0xafd6a648,
0xb8c4b6d7,0xbb99bbce,0x3a6d3b3b,0xb505b303,0xbaddb9ed,0xbaf6bb50,0x381d395f,0xb7e3b67c,0xbbeabb88,0xba0fba8a,0x30b23564,0xb93ab89b,
0x3c003c00,0xba4fb9cb,0,0xb8ecb984,0x3c003c00,0xbb25bac2,0,0xb732b848,0x3c003c00,0xbbb6bb77,0,0xb444b5c2,
0x3c003c00,0xbbfabbe2,0,0xacb5b179,0x33c62a48,0x367c393a,0x3bc33bfe,0xbb50ba0f,0x38c436d7,0xb1792fd6,0x3a6d3b3b,0xbbe2bbf1,
0x3add39ed,0xb984b732,0x381d395f,0xb9cbbb25,0x3bea3b88,0xbbcebaf6,0x30b23564,0xb303b7e3,0xbb0ebbf6,0x3be23a4f,0x378b2e46,0x317938ec,
0xb4a5b913,0x39843b99,0x3ba83a2f,0xb9cbb505,0x378b2e46,0xb3033444,0x3b0e3bf6,0xbbcebbb6,0x3ba83a2f,0xbb77b93a,0x34a53913,0xb5c2ba0f,
0xb95fb0b2,0x2cb5b89b,0xb9edbbea,0x3bfa3a8a,0xbb88bbc3,0x3bf13984,0x3564b3c6,0x2fd639cb,0xaa48b8c4,0x35053ac2,0x3bfe3a6d,0xbb99b848,
0x3b3b381d,0xbaf6b5c2,0x36d73add,0xb7e3bb77,0x38723bd9,0xbb99bac2,0xbaa7b23e,0x3505b848,0xbaa7b23e,0x37e3b5c2,0xb872bbd9,0x3af63b77,
0xb872bbd9,0x3a0f3be2,0x3aa7323e,0xb93a3179,0x3aa7323e,0xba4fa648,0x38723bd9,0xb8ecbbff,0x3b8833c6,0xb84837e3,0x35643bc3,0xbac2baf6,
0xaa483a6d,0xb67cbbfa,0xbbfeb8c4,0x3b502cb5,0xbb3bbadd,0x3be238ec,0x36d7b81d,0xb1793a4f,0x39edb0b2,0xb9843505,0x395f3bea,0xb9cbbb99,
0xae46bba8,0x39843b25,0x3bf634a5,0xb9cb3732,0x3a2f3b0e,0xbbceb7e3,0xb913378b,0x3303baf6,0xbbf6b4a5,0x3b77acb5,0xae46bba8,0x35c23bfa,
0x3913b78b,0xb89b38ec,0x3a2f3b0e,0xba8aba4f,0xbbeab564,0x3af6b67c,0x30b2bb88,0x37e33b50,0x3bc3aa48,0xba0f389b,0x33c63bfe,0xb93aba8a,
0xba6d36d7,0x38ecb9cb,0xb8c4bb3b,0x3a4f3984,0x381db9ed,0xb7323ac2,0x3add395f,0xbb25b848,0xb61f3b64,0xb444bb77,0xbb64b61f,0x3bb6b5c2,
0x361fbb64,0x2cb53be2,0x3b64361f,0xbbfa3179,0xb61f3b64,0x2fd6bbff,0xbb64b61f,0x3bf12648,0x361fbb64,0xb5053bce,0x3b64361f,0xbb99b303,
0x3a6d36d7,0xbbff3505,0xb8c43b3b,0xa648bb99,0xb81db9ed,0x3ac23444,0x3addb95f,0xb8483bb6,0x30b23b88,0xb67cba0f,0xbbea3564,0x3b50b93a,
0x33c6bbfe,0xb1793bf1,0x3bc32a48,0xbbe22fd6,0x3a2fbb0e,0xb3033bb6,0x3913378b,0xbbce3444,0xbbf634a5,0x3b77ba0f,0x2e46bba8,0x35c2393a,
0x3913378b,0xba8aafd6,0xba2f3b0e,0x389bbbf1,0x2e46bba8,0xa6483b25,0x3bf6b4a5,0xbbff3732,0xb6d7b81d,0x3b25b303,0x3b3bbadd,0xb7323bce,
0xb95f3bea,0x3444bb50,0xb9edb0b2,0x3bb6b67c,0x3b88b3c6,0xbbfa389b,0xb5643bc3,0x2cb5ba8a,0xaa48ba6d,0x2fd63984,0x3bfeb8c4,0xbbf139cb,
0xbbd93aa7,0x393abbe2,0xb23eb872,0x3a0fb179,0x323e3872,0xb8eca648,0xbbd93aa7,0x3a4fbbff,0x3bd9baa7,0xbb253bce,0x323e3872,0xb732b303,
0xb23eb872,0x3444367c,0x3bd9baa7,0xbbb63b50,0xaa4838c4,0xb89b2fd6,0xbbfe3a6d,0x3a8abbf1,0x3b3bb81d,0xbbff3b25,0xb6d73add,0xa648b732,
0x39edbbea,0xb8483af6,0x395fb0b2,0xbac237e3,0xb564b3c6,0x367c2cb5,0x3b88bbc3,0xbb503bfa,0x3ba8ba2f,0xbb773bfa,0xb4a53913,0xb5c22cb5,
0x3b0ebbf6,0xb89b3a4f,0x378bae46,0xba8a38ec,0x34a5b913,0xa6483505,0x3ba8ba2f,0xbbff3b99,0xb78b2e46,0x3848b444,0x3b0ebbf6,0xbac23bb6,
0x381db95f,0x2fd6a648,0x3addb9ed,0xbbf13bff,0x30b2b564,0x3505b303,0x3beabb88,0xbb993bce,0xb3c62a48,0x37e3b67c,0x3bc3bbfe,0xbaf63b50,
0xb8c436d7,0x393ab89b,0x3a6dbb3b,0xba0f3a8a,0xb9a839a8,0x3bf1bbff,0x39a8b9a8,0xafd62648,0xb9a839a8,0x3b99bbce,0x39a8b9a8,0xb5053303,
0xb9a839a8,0x3af6bb50,0x39a8b9a8,0xb7e3367c,0xb9a839a8,0x3a0fba8a,0x39a8b9a8,0xb93a389b,0xbadd39ed,0x35c2acb5,0xb81d395f,0x3b77bbfa,
0xbbea3b88,0x3a8ab8ec,0xb0b23564,0x389bba4f,0xbbc33bfe,0x3bffbb99,0x33c6aa48,0x2648b505,0xba6d3b3b,0x3ac2bbb6,0x38c4b6d7,0xb8483444,
0x34a5b913,0xba8a3bf1,0xbba83a2f,0x389bafd6,0xb78b2e46,0x26483732,0xbb0e3bf6,0x3bffbb25,0xbba83a2f,0x3ac2b7e3,0xb4a53913,0x3848baf6,
0xbb0e3bf6,0x3b50bbfa,0x378bae46,0xb67cacb5,0x3bfeba6d,0xba0f3179,0x2a48b8c4,0xb93a3be2,0x36d7badd,0xba4f3bff,0xbb3b381d,0x38ec2648,
0xb95f30b2,0x37323303,0xb9ed3bea,0x3b25bbce,0xbb883bc3,0x3bb6bb50,0x356433c6,0xb444b67c,0x323e3872,0x3732bbce,0x3bd9baa7,0xbb253303,
0x3bd9baa7,0xbbb6367c,0xb23eb872,0xb4443b50,0xb23eb872,0xacb53a8a,0xbbd93aa7,0x3bfab89b,0xbbd93aa7,0x3bf1b9cb,0x323e3872,0xafd6b984,
0xbb3b3add,0x3bceb444,0x36d7381d,0x3303bbb6,0x39ed30b2,0xb5c2b93a,0x395fbbea,0xbb773a0f,0x3564bbc3,0xb89b3bf1,0xbb8833c6,0x3a8a2fd6,
0xbbfe38c4,0x3bffb732,0x2a483a6d,0x2648bb25,0xb913b78b,0x26483b99,0xba2f3b0e,0x3bffb505,0xae463ba8,0x3848bbb6,0x3bf6b4a5,0xbac2b444,
0x3a2fbb0e,0xbb50393a,0xb913b78b,0x367c3a0f,0xbbf634a5,0x3be2afd6,0xae463ba8,0x3179bbf1,0x38c4bb3b,0xbbb635c2,0xba6db6d7,0x34443b77,
0xbadd395f,0x3bfab179,0x381d39ed,0xacb5bbe2,0x3beab564,0xbbf1a648,0xb0b2bb88,0xafd63bff,0xbbc3aa48,0x3b993303,0xb3c63bfe,0x3505bbce,
0x3b64361f,0xb7e3bb50,0x361fbb64,0xbaf6367c,0xbb64b61f,0x393a3a8a,0xb61f3b64,0x3a0fb89b,0x3b64361f,0xba4fb984,0x361fbb64,0xb8ec39cb,
0xbb64b61f,0x3b253848,0xb61f3b64,0x3732bac2,0xb0b23b88,0x39cbb732,0x3bea3564,0xb984bb25,0xb3c6bbfe,0xb3033af6,0xbbc32a48,0x3bce37e3,
0x38c43b3b,0xb5c2bbfa,0x3a6db6d7,0xbb772cb5,0xbaddb95f,0x3a8a3a4f,0xb81d39ed,0x389bb8ec,0xbbf6b4a5,0x3ac23af6,0x2e463ba8,0x3848b7e3,
0x3913b78b,0xbb50acb5,0xba2fbb0e,0x367c3bfa,0x2e463ba8,0x3179ba4f,0x3bf634a5,0xbbe2b8ec,0xba2fbb0e,0x39cb3b99,0xb913378b,0x3984b505,
0xb564bbc3,0xb5053848,0xbb88b3c6,0x3b993ac2,0x3bfe38c4,0xbaf6bb77,0x2a48ba6d,0xb7e335c2,0xb6d7381d,0x393ab179,0x3b3b3add,0xba0fbbe2,
0xb95fbbea,0x38ec3bff,0xb9ed30b2,0x3a4f2648,0x3aa7323e,0xbbfaba8a,0xb872bbd9,0xacb5389b,0x38723bd9,0xafd6b9cb,0x3aa7323e,0xbbf1b984,
0xbaa7b23e,0x3b993848,0x38723bd9,0xb505bac2,0xb872bbd9,0x37e33b77,0xbaa7b23e,0x3af635c2,0x39ed3bea,0xb179b8ec,0x395f30b2,0xbbe2ba4f,
0xb56433c6,0x39cb3505,0x3b883bc3,0xb984bb99,0xbbfeba6d,0x3bce3bb6,0x2a4838c4,0x3303b444,0xb6d7badd,0x35c23a0f,0xbb3bb81d,0x3b77393a,
0xb78bae46,0x3b503a0f,0x3b0e3bf6,0xb67cb93a,0xbba8ba2f,0x3be23bf1,0x34a53913,0x3179afd6,0xbb0ebbf6,0x39cb3b25,0xb78bae46,0x39843732,
0xb4a5b913,0x330337e3,0xbba8ba2f,0x3bce3af6,0xbbc3bbfe,0x38ec3984,0xb3c6aa48,0x3a4f39cb,0xba6dbb3b,0x37323848,0xb8c4b6d7,0x3b253ac2,
0xb81db95f,0x344435c2,0xbaddb9ed,0x3bb63b77,0xb0b2b564,0x2cb53179,0xbbeabb88,0x3bfa3be2,0x3c003c00,0x3a4f39cb,0,0x38ec3984,
0x3c003c00,0x3b253ac2,0,0x37323848,0x3c003c00,0x3bb63b77,0,0x344435c2,0x3c003c00,0x3bfa3be2,0,0x2cb53179,
0x33c62a48,0xb67cb93a,0x3bc33bfe,0x3b503a0f,0x38c436d7,0x3179afd6,0x3a6d3b3b,0x3be23bf1,0x3add39ed,0x39843732,0x381d395f,0x39cb3b25,
0x3bea3b88,0x3bce3af6,0x30b23564,0x330337e3,0xbb0ebbf6,0xbbe2ba4f,0x378b2e46,0xb179b8ec,0xb4a5b913,0xb984bb99,0x3ba83a2f,0x39cb3505,
0x378b2e46,0x3303b444,0x3b0e3bf6,0x3bce3bb6,0x3ba83a2f,0x3b77393a,0x34a53913,0x35c23a0f,0xb95fb0b2,0xacb5389b,0xb9edbbea,0xbbfaba8a,
0xbb88bbc3,0xbbf1b984,0x3564b3c6,0xafd6b9cb,0xaa48b8c4,0xb505bac2,0x3bfe3a6d,0x3b993848,0x3b3b381d,0x3af635c2,0x36d73add,0x37e33b77,
0x38723bd9,0x3b993ac2,0xbaa7b23e,0xb5053848,0xbaa7b23e,0xb7e335c2,0xb872bbd9,0xbaf6bb77,0xb872bbd9,0xba0fbbe2,0x3aa7323e,0x393ab179,
0x3aa7323e,0x3a4f2648,0x38723bd9,0x38ec3bff,0x3b8833c6,0x3848b7e3,0x35643bc3,0x3ac23af6,0xaa483a6d,0x367c3bfa,0xbbfeb8c4,0xbb50acb5,
0xbb3bbadd,0xbbe2b8ec,0x36d7b81d,0x3179ba4f,0x39edb0b2,0x3984b505,0x395f3bea,0x39cb3b99,0xae46bba8,0xb984bb25,0x3bf634a5,0x39cbb732,
0x3a2f3b0e,0x3bce37e3,0xb913378b,0xb3033af6,0xbbf6b4a5,0xbb772cb5,0xae46bba8,0xb5c2bbfa,0x3913b78b,0x389bb8ec,0x3a2f3b0e,0x3a8a3a4f,
0xbbeab564,0xbaf6367c,0x30b2bb88,0xb7e3bb50,0x3bc3aa48,0x3a0fb89b,0x33c63bfe,0x393a3a8a,0xba6d36d7,0xb8ec39cb,0xb8c4bb3b,0xba4fb984,
0x381db9ed,0x3732bac2,0x3add395f,0x3b253848,0xb61f3b64,0x34443b77,0xbb64b61f,0xbbb635c2,0x361fbb64,0xacb5bbe2,0x3b64361f,0x3bfab179,
0xb61f3b64,0xafd63bff,0xbb64b61f,0xbbf1a648,0x361fbb64,0x3505bbce,0x3b64361f,0x3b993303,0x3a6d36d7,0x3bffb505,0xb8c43b3b,0x26483b99,
0xb81db9ed,0xbac2b444,0x3addb95f,0x3848bbb6,0x30b23b88,0x367c3a0f,0xbbea3564,0xbb50393a,0x33c6bbfe,0x3179bbf1,0x3bc32a48,0x3be2afd6,
0x3a2fbb0e,0x3303bbb6,0x3913378b,0x3bceb444,0xbbf634a5,0xbb773a0f,0x2e46bba8,0xb5c2b93a,0x3913378b,0x3a8a2fd6,0xba2f3b0e,0xb89b3bf1,
0x2e46bba8,0x2648bb25,0x3bf6b4a5,0x3bffb732,0xb6d7b81d,0xbb253303,0x3b3bbadd,0x3732bbce,0xb95f3bea,0xb4443b50,0xb9edb0b2,0xbbb6367c,
0x3b88b3c6,0x3bfab89b,0xb5643bc3,0xacb53a8a,0xaa48ba6d,0xafd6b984,0x3bfeb8c4,0x3bf1b9cb,0xbbd93aa7,0xb93a3be2,0xb23eb872,0xba0f3179,
0x323e3872,0x38ec2648,0xbbd93aa7,0xba4f3bff,0x3bd9baa7,0x3b25bbce,0x323e3872,0x37323303,0xb23eb872,0xb444b67c,0x3bd9baa7,0x3bb6bb50,
0xaa4838c4,0x389bafd6,0xbbfe3a6d,0xba8a3bf1,0x3b3bb81d,0x3bffbb25,0xb6d73add,0x26483732,0x39edbbea,0x3848baf6,0x395fb0b2,0x3ac2b7e3,
0xb564b3c6,0xb67cacb5,0x3b88bbc3,0x3b50bbfa,0x3ba8ba2f,0x3b77bbfa,0xb4a53913,0x35c2acb5,0x3b0ebbf6,0x389bba4f,0x378bae46,0x3a8ab8ec,
0x34a5b913,0x2648b505,0x3ba8ba2f,0x3bffbb99,0xb78b2e46,0xb8483444,0x3b0ebbf6,0x3ac2bbb6,0x381db95f,0xafd62648,0x3addb9ed,0x3bf1bbff,
0x30b2b564,0xb5053303,0x3beabb88,0x3b99bbce,0xb3c62a48,0xb7e3367c,0x3bc3bbfe,0x3af6bb50,0xb8c436d7,0xb93a389b,0x3a6dbb3b,0x3a0fba8a,
0xb9a839a8,0xbbf13bff,0x39a8b9a8,0x2fd6a648,0xb9a839a8,0xbb993bce,0x39a8b9a8,0x3505b303,0xb9a839a8,0xbaf63b50,0x39a8b9a8,0x37e3b67c,
0xb9a839a8,0xba0f3a8a,0x39a8b9a8,0x393ab89b,0xbadd39ed,0xb5c22cb5,0xb81d395f,0xbb773bfa,0xbbea3b88,0xba8a38ec,0xb0b23564,0xb89b3a4f,
0xbbc33bfe,0xbbff3b99,0x33c6aa48,0xa6483505,0xba6d3b3b,0xbac23bb6,0x38c4b6d7,0x3848b444,0x34a5b913,0x3a8abbf1,0xbba83a2f,0xb89b2fd6,
0xb78b2e46,0xa648b732,0xbb0e3bf6,0xbbff3b25,0xbba83a2f,0xbac237e3,0xb4a53913,0xb8483af6,0xbb0e3bf6,0xbb503bfa,0x378bae46,0x367c2cb5,
0x3bfeba6d,0x3a0fb179,0x2a48b8c4,0x393abbe2,0x36d7badd,0x3a4fbbff,0xbb3b381d,0xb8eca648,0xb95f30b2,0xb732b303,0xb9ed3bea,0xbb253bce,
0xbb883bc3,0xbbb63b50,0x356433c6,0x3444367c,0x323e3872,0xb7323bce,0x3bd9baa7,0x3b25b303,0x3bd9baa7,0x3bb6b67c,0xb23eb872,0x3444bb50,
0xb23eb872,0x2cb5ba8a,0xbbd93aa7,0xbbfa389b,0xbbd93aa7,0xbbf139cb,0x323e3872,0x2fd63984,0xbb3b3add,0xbbce3444,0x36d7381d,0xb3033bb6,
0x39ed30b2,0x35c2393a,0x395fbbea,0x3b77ba0f,0x3564bbc3,0x389bbbf1,0xbb8833c6,0xba8aafd6,0xbbfe38c4,0xbbff3732,0x2a483a6d,0xa6483b25,
0xb913b78b,0xa648bb99,0xba2f3b0e,0xbbff3505,0xae463ba8,0xb8483bb6,0x3bf6b4a5,0x3ac23444,0x3a2fbb0e,0x3b50b93a,0xb913b78b,0xb67cba0f,
0xbbf634a5,0xbbe22fd6,0xae463ba8,0xb1793bf1,0x38c4bb3b,0x3bb6b5c2,0xba6db6d7,0xb444bb77,0xbadd395f,0xbbfa3179,0x381d39ed,0x2cb53be2,
0x3beab564,0x3bf12648,0xb0b2bb88,0x2fd6bbff,0xbbc3aa48,0xbb99b303,0xb3c63bfe,0xb5053bce,0x3b64361f,0x37e33b50,0x361fbb64,0x3af6b67c,
0xbb64b61f,0xb93aba8a,0xb61f3b64,0xba0f389b,0x3b64361f,0x3a4f3984,0x361fbb64,0x38ecb9cb,0xbb64b61f,0xbb25b848,0xb61f3b64,0xb7323ac2,
0xb0b23b88,0xb9cb3732,0x3bea3564,0x39843b25,0xb3c6bbfe,0x3303baf6,0xbbc32a48,0xbbceb7e3,0x38c43b3b,0x35c23bfa,0x3a6db6d7,0x3b77acb5,
0xbaddb95f,0xba8aba4f,0xb81d39ed,0xb89b38ec,0xbbf6b4a5,0xbac2baf6,0x2e463ba8,0xb84837e3,0x3913b78b,0x3b502cb5,0xba2fbb0e,0xb67cbbfa,
0x2e463ba8,0xb1793a4f,0x3bf634a5,0x3be238ec,0xba2fbb0e,0xb9cbbb99,0xb913378b,0xb9843505,0xb564bbc3,0x3505b848,0xbb88b3c6,0xbb99bac2,
0x3bfe38c4,0x3af63b77,0x2a48ba6d,0x37e3b5c2,0xb6d7381d,0xb93a3179,0x3b3b3add,0x3a0f3be2,0xb95fbbea,0xb8ecbbff,0xb9ed30b2,0xba4fa648,
0x3aa7323e,0x3bfa3a8a,0xb872bbd9,0x2cb5b89b,0x38723bd9,0x2fd639cb,0x3aa7323e,0x3bf13984,0xbaa7b23e,0xbb99b848,0x38723bd9,0x35053ac2,
0xb872bbd9,0xb7e3bb77,0xbaa7b23e,0xbaf6b5c2,0x39ed3bea,0x317938ec,0x395f30b2,0x3be23a4f,0xb56433c6,0xb9cbb505,0x3b883bc3,0x39843b99,
0xbbfeba6d,0xbbcebbb6,0x2a4838c4,0xb3033444,0xb6d7badd,0xb5c2ba0f,0xbb3bb81d,0xbb77b93a,0xb78bae46,0xbb50ba0f,0x3b0e3bf6,0x367c393a,
0xbba8ba2f,0xbbe2bbf1,0x34a53913,0xb1792fd6,0xbb0ebbf6,0xb9cbbb25,0xb78bae46,0xb984b732,0xb4a5b913,0xb303b7e3,0xbba8ba2f,0xbbcebaf6,
0xbbc3bbfe,0xb8ecb984,0xb3c6aa48,0xba4fb9cb,0xba6dbb3b,0xb732b848,0xb8c4b6d7,0xbb25bac2,0xb81db95f,0xb444b5c2,0xbaddb9ed,0xbbb6bb77,
0xb0b2b564,0xacb5b179,0xbbeabb88,0xbbfabbe2,0x3c003c00,0x96480000,0x3c003c00,0xa311a248,0x3c003c00,0x9cb69a48,0x3c003c00,0xa452a3db,
0x3c003c00,0x9fdb9e48,0x3c003c00,0xa51ba4b6,0x3c003c00,0xa17fa0b6,0x3bff3c00,0xa5e4a57f,0x3c003c00,0x9fdb0000,0x3bfb3bfc,0xac6aabd9,
0x3bff3c00,0xa5e4a3db,0x3bf93bfa,0xad65ace7,0x3bfe3bff,0xa8e8a7da,0x3bf63bf7,0xae5fade2,0x3bfd3bfe,0xaadea9e3,0x3bf23bf4,0xaf59aedc,
0x3c003c00,0xa3110000,0x3bf03bf4,0xafefaf0e,0x3bfe3bff,0xa94da711,0x3be83bed,0xb0d7b067,0x3bfb3bfd,0xac6aab11,0x3bdf3be4,0xb1b6b147,
0x3bf63bf9,0xae2dad4c,0x3bd43bda,0xb294b226,0x3c003c00,0xa51b0000,0x3bdf3be6,0xb1b6b115,0x3bfc3bfe,0xaba7a91b,0x3bcf3bd7,0xb2f7b257,
0x3bf63bf9,0xae5fad1a,0x3bbc3bc6,0xb41ab396,0x3bec3bf1,0xb074afa4,0x3ba53bb1,0xb4b7b469,0x3bff3c00,0xa6ad0000,0x3bc83bd4,0xb371b2a1,
0x3bfa3bfd,0xad00aaac,0x3bac3bbb,0xb487b420,0x3bef3bf5,0xb029aeaa,0x3b8b3b9d,0xb552b4ed,0x3bde3be7,0xb1cfb0fd,0x3b653b79,0xb61ab5b6,
0x3bff3c00,0xa81f0000,0x3bab3bbc,0xb493b414,0x3bf63bfc,0xae2dac1f,0x3b813b97,0xb58db511,0x3be53bef,0xb122b01d,0x3b4f3b69,0xb682b608,
0x3bcc3bda,0xb328b226,0x3b163b33,0xb76fb6f9,0x3bfe3c00,0xa8e80000,0x3b873ba0,0xb56ab4d5,0x3bf23bfa,0xaf59ace7,0x3b4c3b6b,0xb68db5fd,
0x3bda3be8,0xb219b0e4,0x3b073b2b,0xb7a6b71b,0x3bb73bca,0xb43eb34c,0x3ab63ae0,0xb85ab817,0x3bfe3c00,0xa9b10000,0x3b5e3b80,0xb63cb593,
0x3bee3bf8,0xb042adb0,0x3b103b39,0xb785b6e3,0x3bce3be0,0xb30fb1aa,0x3ab33ae3,0xb85fb812,0x3b9e3bb7,0xb4e7b438,0x3a493a7f,0xb8f3b8ab,
0x3bfd3c00,0xaa7a0000,0x3b2f3b5a,0xb70ab64e,0x3be83bf6,0xb0d7ae78,0x3acb3aff,0xb83ab7c2,0x3bbf3bd6,0xb402b26f,0x3a543a92,0xb8e5b891,
0x3b813ba2,0xb58db4c9,0x39cd3a13,0xb982b935,0x3bfd3c00,0xab430000,0x3afb3b30,0xb7d2b705,0x3be23bf3,0xb16caf40,0x3a7e3abf,0xb8adb84d,
0x3bae3bcb,0xb47bb334,0x39eb3a37,0xb962b909,0x3b603b8a,0xb631b558,0x3946399b,0xba04b9b5,0x3bfc3c00,0xac060000,0x3ac13b02,0xb84ab7b7,
0x3bdc3bf0,0xb201b004,0x3a293a78,0xb91bb8b5,0x3b9c3bc0,0xb4f3b3f7,0x397939d4,0xb9d6b97b,0x3b3d3b70,0xb6d2b5e5,0x38b23918,0xba7aba2b,
0x3bfb3c00,0xac6a0000,0x3a813ad0,0xb8a8b832,0x3bd43bed,0xb294b067,0x39cd3a2b,0xb982b918,0x3b873bb2,0xb56ab45d,0x38fd3969,0xba41b9e5,
0x3b163b53,0xb76fb670,0x3815388c,0xbae1ba95,0x3bfa3c00,0xacce0000,0x3a3d3a99,0xb902b887,0x3bcc3be9,0xb328b0cb,0x396b39d8,0xb9e3b976,
0x3b713ba4,0xb5dfb4bd,0x387a38f6,0xbaa2ba47,0x3aeb3b33,0xb805b6f9,0x36dd37ee,0xbb3abaf3,0x3bf93c00,0xad330000,0x39f43a5e,0xb958b8d8,
0x3bc33be5,0xb3bab12e,0x39023980,0xba3db9d0,0x3b593b95,0xb654b51d,0x37dd387c,0xbaf7baa0,0x3abd3b11,0xb850b780,0x358136b5,0xbb83bb43,
0x3bf83c00,0xad970000,0x39a63a1f,0xb9aab927,0x3bba3be1,0xb426b191,0x38943922,0xba90ba23,0x3b3f3b84,0xb6c6b57c,0x36bb37f9,0xbb42baf0,
0x3a8c3aed,0xb899b802,0x341a3570,0xbbbcbb86,0x3bf73c00,0xadfb0000,0x395439dc,0xb9f8b972,0x3bb03bdc,0xb46fb1f4,0x382038bf,0xbadbba71,
0x3b243b72,0xb737b5da,0x358d36ee,0xbb81bb36,0x3a583ac6,0xb8e0b842,0x31533420,0xbbe3bbbb,0x3bf63c00,0xae5f0000,0x38fd3996,0xba41b9ba,
0x3ba53bd7,0xb4b7b257,0x374e3858,0xbb1ebab8,0x3b073b5f,0xb7a6b637,0x345735da,0xbbb3bb72,0x3a213a9c,0xb924b881,0x2cce3191,0xbbfabbe1,
0x3bf53c00,0xaec30000,0x38a3394d,0xba85b9fe,0x3b9a3bd2,0xb4ffb2b9,0x365437d8,0xbb59baf9,0x3ae83b4b,0xb80ab693,0x323234bd,0xbbd9bba4,
0x39e73a71,0xb966b8bf,0xa4522db0,0xbc00bbf8,0x3bf33c00,0xaf270000,0x38453900,0xbac4ba3f,0x3b8e3bcd,0xb546b31b,0x355236f9,0xbb8bbb33,
0x3ac73b36,0xb840b6ee,0x2f593334,0xbbf2bbcb,0x39aa3a43,0xb9a6b8fb,0xaef51a48,0xbbf4bc00,0x3bf23c00,0xaf8b0000,0x37c838b0,0xbafeba7c,
0x3b813bc7,0xb58db37d,0x344b3614,0xbbb5bb67,0x3aa53b20,0xb874b748,0x288430e4,0xbbffbbe8,0x396b3a13,0xb9e3b935,0xb263ad4c,0xbbd7bbf9,
0x3bf03c00,0xafef0000,0x36ff385d,0xbb32bab5,0x3b733bc1,0xb5d4b3df,0x327c3529,0xbbd6bb93,0x3a813b08,0xb8a8b7a1,0xa9b12d1a,0xbbfebbf9,
0x392939e1,0xba1db96d,0xb49fb160,0xbba9bbe3,0x3bef3c00,0xb0290000,0x36313807,0xbb60bae9,0x3b653bbb,0xb61ab420,0x305b3438,0xbbedbbb7,
0x3a5c3af0,0xb8dbb7f9,0xafef1e48,0xbbf0bc00,0x38e539ad,0xba54b9a4,0xb602b408,0xbb6abbbe,0x3bed3c00,0xb05b0000,0x355e375e,0xbb89bb1a,
0x3b573bb4,0xb65fb451,0x2c6a3288,0xbbfbbbd5,0x3a353ad6,0xb90cb828,0xb27cac51,0xbbd6bbfb,0x389e3976,0xba89b9d8,0xb759b558,0xbb1bbb8a,
0x3beb3c00,0xb08d0000,0x348736aa,0xbbacbb46,0x3b473bad,0xb6a4b481,0x16483099,0xbc00bbeb,0x3a0d3abc,0xb93cb852,0xb47bb080,0xbbaebbec,
0x3855393e,0xbababa0b,0xb850b69e,0xbabdbb49,0x3be93c00,0xb0be0000,0x335935f1,0xbbc9bb6e,0x3b373ba6,0xb6e8b4b1,0xac382d4c,0xbbfcbbf9,
0x39e33aa0,0xb96bb87c,0xb5b1b2d2,0xbb7abbd1,0x380a3905,0xbae8ba3b,0xb8eab7d8,0xba50baf9,0x3be73c00,0xb0f00000,0x319e3534,0xbbe0bb91,
0x3b273b9e,0xb72cb4e1,0xb042257f,0xbbeebc00,0x39b83a83,0xb999b8a6,0xb6ddb48d,0xbb3abbab,0x377a38c9,0xbb13ba69,0xb979b881,0xb9d6ba9c,
0x3be53c00,0xb1220000,0x2fbd3475,0xbbf1bbaf,0x3b163b97,0xb76fb511,0xb263a91b,0xbbd7bbfe,0x398b3a65,0xb9c5b8ce,0xb7feb5ab,0xbaeebb7b,
0x36dd388c,0xbb3aba95,0xb9fcb90e,0xb94fba33,0x3be33c00,0xb1530000,0x2c383365,0xbbfcbbc9,0x3b043b8f,0xb7b2b540,0xb43eae78,0xbbb7bbf6,
0x395d3a47,0xb9f0b8f6,0xb889b6c1,0xba97bb41,0x363c384d,0xbb5ebabf,0xba73b992,0xb8bcb9be,0x3be13c00,0xb1850000,0x217f31db,0xbc00bbdd,
0x3af13b86,0xb7f3b570,0xb546b12e,0xbb8ebbe5,0x392e3a27,0xba19b91d,0xb90cb7cd,0xba35bafc,0x3599380d,0xbb7fbae6,0xbadbba0b,0xb820b93e,
0x3bdf3c00,0xb1b60000,0xa9b1304e,0xbbfebbed,0x3ade3b7d,0xb81ab59f,0xb648b31b,0xbb5cbbcd,0x38fd3a07,0xba41b943,0xb986b867,0xb9c9baae,
0x34f33796,0xbb9cbb0b,0xbb35ba78,0xb6f4b8b5,0x3bdd3c00,0xb1e80000,0xae5f2d7e,0xbbf6bbf8,0x3acb3b74,0xb83ab5ce,0xb742b481,0xbb21bbad,
0x38cc39e5,0xba67b969,0xb9f8b8e2,0xb954ba56,0x344b3710,0xbbb5bb2e,0xbb7fbad9,0xb599b822,0x3bda3c00,0xb2190000,0xb0f028b6,0xbbe7bbff,
0x3ab63b6b,0xb85ab5fd,0xb81ab570,0xbadebb86,0x389939c3,0xba8cb98d,0xba60b956,0xb8d6b9f6,0x33403687,0xbbcbbb4e,0xbbb8bb2e,0xb432b710,
0x3bff3bff,0xa6ada648,0x3bfe3bff,0xa8e8a8b6,0x3bff3bff,0xa776a711,0x3bfe3bfe,0xa94da91b,0x3bff3bff,0xa81fa7da,0x3bfe3bfe,0xa9b1a97f,
0x3bff3bff,0xa884a852,0x3bfe3bfe,0xaa16a9e3,0x3bef3bf1,0xb029afd6,0x3bda3bdd,0xb219b1db,0x3bea3bed,0xb0a6b067,0x3bd43bd7,0xb294b257,
0x3be53be8,0xb122b0e4,0x3bce3bd1,0xb30fb2d2,0x3be03be3,0xb19eb160,0x3bc63bca,0xb389b34c,0x3bc83bce,0xb371b303,0x3b873b91,0xb56ab534,
0x3bba3bc1,0xb426b3df,0x3b733b7d,0xb5d4b59f,0x3bab3bb2,0xb493b45d,0x3b5e3b69,0xb63cb608,0x3b9a3ba2,0xb4ffb4c9,0x3b473b53,0xb6a4b670,
0x3b8b3b99,0xb552b505,0x3b073b1a,0xb7a6b75e,0x3b6f3b7d,0xb5ebb59f,0x3ade3af3,0xb81ab7ee,0x3b4f3b5f,0xb682b637,0x3ab33ac9,0xb85fb83d,
0x3b2c3b3e,0xb715b6cc,0x3a853a9c,0xb8a3b881,0x3b3a3b50,0xb6ddb67c,0x3a5c3a7c,0xb8dbb8b0,0x3b0a3b22,0xb79bb73d,0x3a193a3b,0xb92eb905,
0x3ad53af0,0xb82ab7f9,0x39d239f6,0xb97db956,0x3a9b3ab8,0xb884b858,0x398639ad,0xb9c9b9a4,0x3ad53af6,0xb82ab7e3,0x398b39ba,0xb9c5b996,
0x3a8c3ab1,0xb899b862,0x3929395b,0xba1db9f2,0x3a3d3a65,0xb902b8ce,0x38c138f6,0xba6fba47,0x39e73a13,0xb966b935,0x3855388c,0xbababa95,
0x3a5c3a8a,0xb8dbb89b,0x389938d8,0xba8cba5e,0x39f83a2b,0xb954b918,0x38153858,0xbae1bab8,0x398b39c3,0xb9c5b98d,0x371537a1,0xbb2cbb08,
0x39163951,0xba2db9fa,0x35f73687,0xbb6cbb4e,0x39d23a0f,0xb97db93a,0x371537b7,0xbb2cbb02,0x394f3992,0xb9fcb9be,0x35c83670,0xbb76bb53,
0x38c13909,0xba6fba37,0x346f351d,0xbbb0bb95,0x382a3877,0xbad5baa3,0x3219337d,0xbbdabbc7,0x39373984,0xba11b9cb,0x34cf3593,0xbba1bb80,
0x389438e7,0xba90ba52,0x327c3408,0xbbd6bbbe,0x37c8383d,0xbafebac9,0x2e9130e4,0xbbf5bbe8,0x36543710,0xbb59bb2e,0x16482aac,0xbc00bbfd,
0x388e38ec,0xba93ba4f,0x30d732a1,0xbbe8bbd4,0x3790382d,0xbb0dbad3,0x28e82e14,0xbbfebbf7,0x35eb36c1,0xbb6fbb41,0xaccea4b6,0xbbfabc00,
0x34323511,0xbbb8bb97,0xb201b036,0xbbdcbbee,0x37b23848,0xbb04bac2,0x96482bd9,0xbc00bbfc,0x35df36cc,0xbb71bb3e,0xb010ac1f,0xbbefbbfc,
0x33eb34ed,0xbbc0bb9d,0xb402b20d,0xbbbfbbdb,0x2fef31f4,0xbbf0bbdc,0xb5ebb4f9,0xbb6fbb9b,0x36313732,0xbb60bb25,0xb0f0ad7e,0xbbe7bbf8,
0x341a3529,0xbbbcbb93,0xb49fb31b,0xbba9bbcd,0x2fbd320d,0xbbf1bbdb,0xb6afb5ab,0xbb45bb7b,0xa4522aac,0xbc00bbfd,0xb850b7ac,0xbabdbb05,
0x349f35c2,0xbba9bb77,0xb4dbb365,0xbb9fbbc9,0x308d32ea,0xbbebbbd0,0xb715b5fd,0xbb2cbb6b,0x9fdb2c51,0xbc00bbfb,0xb894b812,0xba90bae3,
0xb109ad4c,0xbbe6bbf9,0xb982b90e,0xb9cdba33,0x32013444,0xbbdcbbb6,0xb721b5f1,0xbb2abb6e,0x26ad2edc,0xbbffbbf4,0xb8adb822,0xba7ebad9,
0xb05bab11,0xbbedbbfd,0xb9aab930,0xb9a6ba17,0xb4b7b2ea,0xbba5bbd0,0xba81ba1b,0xb8a8b92b,0x2d653179,0xbbf9bbe2,0xb89eb807,0xba89bae9,
0xadc99a48,0xbbf8bc00,0xb9afb92b,0xb9a1ba1b,0xb432b1aa,0xbbb8bbe0,0xba93ba27,0xb88eb91d,0xb6d2b587,0xbb3dbb82,0xbb45baf3,0xb6afb7ee,
0xa51b2cb5,0xbc00bbfa,0xb990b900,0xb9c0ba3f,0xb294af40,0xbbd4bbf3,0xba89ba13,0xb89eb935,0xb625b4bd,0xbb63bba4,0xbb47baf0,0xb6a4b7f9,
0xb865b780,0xbab0bb11,0xbbc5bb8f,0xb3a2b540,0xafefa648,0xbbf0bbff,0xba60b9dc,0xb8d6b972,0xb517b31b,0xbb96bbcd,0xbb35bad3,0xb6f4b82d,
0xb7feb693,0xbaeebb4b,0xbbc0bb84,0xb3ebb57c,0xb94ab8ab,0xba00ba7f,0xbbfdbbe9,0xaa7ab0cb,0xb340afd6,0xbbcbbbf1,0xbb0aba99,0xb79bb887,
0xb6d2b540,0xbb3dbb8f,0xbbaebb67,0xb47bb614,0xb8dbb828,0xba5cbad6,0xbbfbbbe0,0xac9cb1aa,0xba15b980,0xb933b9d0,0xbbecbbff,0x30742852,
0xb53ab303,0xbb90bbce,0xbb89bb30,0xb55eb705,0xb83ab6e3,0xbacbbb39,0xbbf2bbca,0xaf8bb34c,0xb9a1b8f6,0xb9afba47,0xbbf5bc00,0x2ec39e48,
0xbac1ba3b,0xb84ab905,0xbb92bbd0,0x352f32ea,0xb6c6b505,0xbb3fbb99,0xbbdcbba0,0xb201b4d5,0xb8fdb838,0xba41bacc,0xbbfebbfb,0x2a16ac83,
0xba50b9b1,0xb8eab99f,0xbbaebbe4,0x347b3147,0xbb4abad9,0xb699b822,0xbaf1bb5d,0x37f33642,0xb820b67c,0xbadbbb50,0xbbffbbe6,0xa884b115,
0xb9afb8f1,0xb9a1ba4b,0xbbd2bbf8,0x32c62db0,0xbae5ba56,0xb80fb8e2,0xbb2abb8c,0x3721354c,0xbbaebb58,0xb47bb659,0xba11baaa,0x3937386d,
0xb8d1b7e3,0xba64baf6,0xbbf2bc00,0x2f8ba248,0xba4db99b,0xb8eeb9b5,0xbb6fbbc1,0x35eb33df,0xbb5cbae3,0xb648b812,0xba6bbafc,0x38c737cd,
0xbbebbbb4,0xb08db451,0xb8f8b9be,0x3a453992,0xb974b89b,0xb9daba8a,0xbbb5bbed,0x344b304e,0xbad5ba33,0xb82ab90e,0xbad8bb58,0x38253659,
0xbbb3bb55,0xb457b665,0xb979ba37,0x39d63909,0xbc00bbed,0x9648b067,0xb764b8a0,0x3b183a87,0xba09b93a,0xb941ba0f,0xbb4abbaf,0x36993475,
0xbb45bab8,0xb6afb858,0xba11babf,0x3937384d,0xbbeabbab,0xb0a6b48d,0xb85ab943,0x3ab63a07,0xbbecbc00,0x30749a48,0xb493b6b5,0x3bab3b43,
0xba8cb9cb,0xb899b984,0xbab3bb46,0x385f36aa,0xbb9cbb28,0xb4f3b726,0xb91fb9fa,0x3a253951,0xbc00bbe4,0xa452b147,0xb631b828,0x3b603ad6,
0xbbb0bbee,0x346f3036,0xae5fb3df,0x3bf63bc1,0xbafeba4f,0xb7c8b8ec,0xb9f4bab5,0x3958385d,0xbbd8bb82,0xb24bb587,0xb80ab90e,0x3ae83a33,
0xbbf3bbfe,0x2f27a97f,0xb2f7b5da,0x3bcf3b72,0xbb4cbbb7,0x368d3438,0x2dc9ac1f,0x3bf83bfc,0xbb5cbac2,0xb648b848,0xb911b9fe,0x3a31394d,
0xbbf9bbc4,0xad33b3ae,0xb5b1b802,0x3b7a3aed,0xbbc5bbf9,0x33a22d1a,0xa94db26f,0x3bfe3bd6,0xbac4bb5d,0x38453642,0x346f2fa4,0x3bb03bf1,
0xbba5bb25,0xb4b7b732,0xb80fb927,0x3ae53a1f,0xbbffbbee,0x2884b036,0xb24bb5b6,0x3bd83b79,0xbb76bbd6,0x35c8326f,0x305ba7da,0x3bed3bff,
0xba19bae0,0x392e3817,0x374234c9,0x3b213ba2,0xbbd9bb77,0xb232b5c2,0xb5ebb832,0x3b6f3ad0,0xbbe8bc00,0x30d7a57f,0xa81fb288,0x3bff3bd5,
0xbb07bb95,0x37a6351d,0x34f33080,0x3b9c3bec,0xb94fba43,0x39fc38fb,0x38ea3780,0x3a503b11,0xbbf8bbb6,0xadc9b444,0xb328b64e,0x3bcc3b5a,
0xbbb7bbf8,0x343e2db0,0x3042a9e3,0x3bee3bfe,0xba7abb36,0x38b236ee,0x379034ed,0x3b0d3b9d,0xb86ab989,0x3aac39c7,0x3a0438fb,0x39463a43,
0xbc00bbe2,0x2311b179,0xac9cb414,0x3bfb3bbc,0xbb6abbd7,0x36023257,0x34b72f40,0x3ba53bf3,0xb9d2babc,0x397d3852,0x38f83775,0x3a453b14,
0xb6ddb8b5,0x3b3a3a78,0x3ae83a0b,0x380a393e,0xbbf2bbfa,0x2f8bacb5,0x2d33af0e,0x3bf93bf4,0xbb04bb9e,0x37b234e1,0x372c3451,0x3b273bb4,
0xb911ba27,0x3a31391d,0x3a0038e2,0x394a3a56,0xb4c3b796,0x3ba33b0b,0x3b8b3ae6,0x3552380d,0x4c004c00,0x26480000,0x4c004c00,0x33113248,
0x4c004c00,0x2cb62a48,0x4c004c00,0x345233db,0x4c004c00,0x2fdb2e48,0x4c004c00,0x351b34b6,0x4c004c00,0x317f30b6,0x4bff4c00,0x35e4357f,
0x4c004c00,0x2fdb0000,0x4bfb4bfc,0x3c6a3bd9,0x4bff4c00,0x35e433db,0x4bf94bfa,0x3d653ce7,0x4bfe4bff,0x38e837da,0x4bf64bf7,0x3e5f3de2,
0x4bfd4bfe,0x3ade39e3,0x4bf24bf4,0x3f593edc,0x4c004c00,0x33110000,0x4bf04bf4,0x3fef3f0e,0x4bfe4bff,0x394d3711,0x4be84bed,0x40d74067,
0x4bfb4bfd,0x3c6a3b11,0x4bdf4be4,0x41b64147,0x4bf64bf9,0x3e2d3d4c,0x4bd44bda,0x42944226,0x4c004c00,0x351b0000,0x4bdf4be6,0x41b64115,
0x4bfc4bfe,0x3ba7391b,0x4bcf4bd7,0x42f74257,0x4bf64bf9,0x3e5f3d1a,0x4bbc4bc6,0x441a4396,0x4bec4bf1,0x40743fa4,0x4ba54bb1,0x44b74469,
0x4bff4c00,0x36ad0000,0x4bc84bd4,0x437142a1,0x4bfa4bfd,0x3d003aac,0x4bac4bbb,0x44874420,0x4bef4bf5,0x40293eaa,0x4b8b4b9d,0x455244ed,
0x4bde4be7,0x41cf40fd,0x4b654b79,0x461a45b6,0x4bff4c00,0x381f0000,0x4bab4bbc,0x44934414,0x4bf64bfc,0x3e2d3c1f,0x4b814b97,0x458d4511,
0x4be54bef,0x4122401d,0x4b4f4b69,0x46824608,0x4bcc4bda,0x43284226,0x4b164b33,0x476f46f9,0x4bfe4c00,0x38e80000,0x4b874ba0,0x456a44d5,
0x4bf24bfa,0x3f593ce7,0x4b4c4b6b,0x468d45fd,0x4bda4be8,0x421940e4,0x4b074b2b,0x47a6471b,0x4bb74bca,0x443e434c,0x4ab64ae0,0x485a4817,
0x4bfe4c00,0x39b10000,0x4b5e4b80,0x463c4593,0x4bee4bf8,0x40423db0,0x4b104b39,0x478546e3,0x4bce4be0,0x430f41aa,0x4ab34ae3,0x485f4812,
0x4b9e4bb7,0x44e74438,0x4a494a7f,0x48f348ab,0x4bfd4c00,0x3a7a0000,0x4b2f4b5a,0x470a464e,0x4be84bf6,0x40d73e78,0x4acb4aff,0x483a47c2,
0x4bbf4bd6,0x4402426f,0x4a544a92,0x48e54891,0x4b814ba2,0x458d44c9,0x49cd4a13,0x49824935,0x4bfd4c00,0x3b430000,0x4afb4b30,0x47d24705,
0x4be24bf3,0x416c3f40,0x4a7e4abf,0x48ad484d,0x4bae4bcb,0x447b4334,0x49eb4a37,0x49624909,0x4b604b8a,0x46314558,0x4946499b,0x4a0449b5,
0x4bfc4c00,0x3c060000,0x4ac14b02,0x484a47b7,0x4bdc4bf0,0x42014004,0x4a294a78,0x491b48b5,0x4b9c4bc0,0x44f343f7,0x497949d4,0x49d6497b,
0x4b3d4b70,0x46d245e5,0x48b24918,0x4a7a4a2b,0x4bfb4c00,0x3c6a0000,0x4a814ad0,0x48a84832,0x4bd44bed,0x42944067,0x49cd4a2b,0x49824918,
0x4b874bb2,0x456a445d,0x48fd4969,0x4a4149e5,0x4b164b53,0x476f4670,0x4815488c,0x4ae14a95,0x4bfa4c00,0x3cce0000,0x4a3d4a99,0x49024887,
0x4bcc4be9,0x432840cb,0x496b49d8,0x49e34976,0x4b714ba4,0x45df44bd,0x487a48f6,0x4aa24a47,0x4aeb4b33,0x480546f9,0x46dd47ee,0x4b3a4af3,
0x4bf94c00,0x3d330000,0x49f44a5e,0x495848d8,0x4bc34be5,0x43ba412e,0x49024980,0x4a3d49d0,0x4b594b95,0x4654451d,0x47dd487c,0x4af74aa0,
0x4abd4b11,0x48504780,0x458146b5,0x4b834b43,0x4bf84c00,0x3d970000,0x49a64a1f,0x49aa4927,0x4bba4be1,0x44264191,0x48944922,0x4a904a23,
0x4b3f4b84,0x46c6457c,0x46bb47f9,0x4b424af0,0x4a8c4aed,0x48994802,0x441a4570,0x4bbc4b86,0x4bf74c00,0x3dfb0000,0x495449dc,0x49f84972,
0x4bb04bdc,0x446f41f4,0x482048bf,0x4adb4a71,0x4b244b72,0x473745da,0x458d46ee,0x4b814b36,0x4a584ac6,0x48e04842,0x41534420,0x4be34bbb,
0x4bf64c00,0x3e5f0000,0x48fd4996,0x4a4149ba,0x4ba54bd7,0x44b74257,0x474e4858,0x4b1e4ab8,0x4b074b5f,0x47a64637,0x445745da,0x4bb34b72,
0x4a214a9c,0x49244881,0x3cce4191,0x4bfa4be1,0x4bf54c00,0x3ec30000,0x48a3494d,0x4a8549fe,0x4b9a4bd2,0x44ff42b9,0x465447d8,0x4b594af9,
0x4ae84b4b,0x480a4693,0x423244bd,0x4bd94ba4,0x49e74a71,0x496648bf,0xb4523db0,0x4c004bf8,0x4bf34c00,0x3f270000,0x48454900,0x4ac44a3f,
0x4b8e4bcd,0x4546431b,0x455246f9,0x4b8b4b33,0x4ac74b36,0x484046ee,0x3f594334,0x4bf24bcb,0x49aa4a43,0x49a648fb,0xbef52a48,0x4bf44c00,
0x4bf24c00,0x3f8b0000,0x47c848b0,0x4afe4a7c,0x4b814bc7,0x458d437d,0x444b4614,0x4bb54b67,0x4aa54b20,0x48744748,0x388440e4,0x4bff4be8,
0x496b4a13,0x49e34935,0xc263bd4c,0x4bd74bf9,0x4bf04c00,0x3fef0000,0x46ff485d,0x4b324ab5,0x4b734bc1,0x45d443df,0x427c4529,0x4bd64b93,
0x4a814b08,0x48a847a1,0xb9b13d1a,0x4bfe4bf9,0x492949e1,0x4a1d496d,0xc49fc160,0x4ba94be3,0x4bef4c00,0x40290000,0x46314807,0x4b604ae9,
0x4b654bbb,0x461a4420,0x405b4438,0x4bed4bb7,0x4a5c4af0,0x48db47f9,0xbfef2e48,0x4bf04c00,0x48e549ad,0x4a5449a4,0xc602c408,0x4b6a4bbe,
0x4bed4c00,0x405b0000,0x455e475e,0x4b894b1a,0x4b574bb4,0x465f4451,0x3c6a4288,0x4bfb4bd5,0x4a354ad6,0x490c4828,0xc27cbc51,0x4bd64bfb,
0x489e4976,0x4a8949d8,0xc759c558,0x4b1b4b8a,0x4beb4c00,0x408d0000,0x448746aa,0x4bac4b46,0x4b474bad,0x46a44481,0x26484099,0x4c004beb,
0x4a0d4abc,0x493c4852,0xc47bc080,0x4bae4bec,0x4855493e,0x4aba4a0b,0xc850c69e,0x4abd4b49,0x4be94c00,0x40be0000,0x435945f1,0x4bc94b6e,
0x4b374ba6,0x46e844b1,0xbc383d4c,0x4bfc4bf9,0x49e34aa0,0x496b487c,0xc5b1c2d2,0x4b7a4bd1,0x480a4905,0x4ae84a3b,0xc8eac7d8,0x4a504af9,
0x4be74c00,0x40f00000,0x419e4534,0x4be04b91,0x4b274b9e,0x472c44e1,0xc042357f,0x4bee4c00,0x49b84a83,0x499948a6,0xc6ddc48d,0x4b3a4bab,
0x477a48c9,0x4b134a69,0xc979c881,0x49d64a9c,0x4be54c00,0x41220000,0x3fbd4475,0x4bf14baf,0x4b164b97,0x476f4511,0xc263b91b,0x4bd74bfe,
0x498b4a65,0x49c548ce,0xc7fec5ab,0x4aee4b7b,0x46dd488c,0x4b3a4a95,0xc9fcc90e,0x494f4a33,0x4be34c00,0x41530000,0x3c384365,0x4bfc4bc9,
0x4b044b8f,0x47b24540,0xc43ebe78,0x4bb74bf6,0x495d4a47,0x49f048f6,0xc889c6c1,0x4a974b41,0x463c484d,0x4b5e4abf,0xca73c992,0x48bc49be,
0x4be14c00,0x41850000,0x317f41db,0x4c004bdd,0x4af14b86,0x47f34570,0xc546c12e,0x4b8e4be5,0x492e4a27,0x4a19491d,0xc90cc7cd,0x4a354afc,
0x4599480d,0x4b7f4ae6,0xcadbca0b,0x4820493e,0x4bdf4c00,0x41b60000,0xb9b1404e,0x4bfe4bed,0x4ade4b7d,0x481a459f,0xc648c31b,0x4b5c4bcd,
0x48fd4a07,0x4a414943,0xc986c867,0x49c94aae,0x44f34796,0x4b9c4b0b,0xcb35ca78,0x46f448b5,0x4bdd4c00,0x41e80000,0xbe5f3d7e,0x4bf64bf8,
0x4acb4b74,0x483a45ce,0xc742c481,0x4b214bad,0x48cc49e5,0x4a674969,0xc9f8c8e2,0x49544a56,0x444b4710,0x4bb54b2e,0xcb7fcad9,0x45994822,
0x4bda4c00,0x42190000,0xc0f038b6,0x4be74bff,0x4ab64b6b,0x485a45fd,0xc81ac570,0x4ade4b86,0x489949c3,0x4a8c498d,0xca60c956,0x48d649f6,
0x43404687,0x4bcb4b4e,0xcbb8cb2e,0x44324710,0x4bd84c00,0x424b0000,0xc2adb248,0x4bd34c00,0x4aa24b62,0x487a462b,0xc88ec659,0x4a934b58,
0x4865499f,0x4ab049b1,0xcabdc9c3,0x4850498d,0x41e845fd,0x4bdd4b6b,0xcbe1cb74,0x418545ce,0x4bd64c00,0x427c0000,0xc432bbd9,0x4bb84bfc,
0x4a8c4b58,0x48994659,0xc8fdc73d,0x4a414b22,0x4830497b,0x4ad149d4,0xcb10ca27,0x4785491d,0x408d4570,0x4beb4b86,0xcbf9cbad,0x3d334481,
0x4bd34c00,0x42ad0000,0xc50bbf0e,0x4b984bf4,0x4a764b4e,0x48b74687,0xc966c80d,0x49e74ae6,0x47f34956,0x4af149f6,0xcb57ca83,0x465f48a6,
0x3e5f44e1,0x4bf64b9e,0xcc00cbd7,0xb17f4257,0x4bd04c00,0x42de0000,0xc5dfc115,0x4b714be6,0x4a604b43,0x48d646b5,0xc9c9c877,0x49864aa3,
0x47854930,0x4b104a17,0xcb92cad6,0x452f4828,0x3b434451,0x4bfd4bb4,0xcbf5cbf3,0xbe913f40,0x4bce4c00,0x430f0000,0xc6afc2a1,0x4b454bd4,
0x4a494b39,0x48f346e3,0xca25c8dd,0x491f4a5a,0x47154909,0x4b2c4a37,0xcbc0cb20,0x43eb4748,0x3311437d,0x4c004bc7,0xcbd9cbff,0xc2323711,
0x4bcb4c00,0x43400000,0xc77ac414,0x4b134bbc,0x4a314b2e,0x49114710,0xca7ac93e,0x48b24a0b,0x46a448e2,0x4b474a56,0xcbe2cb5f,0x416c4637,
0xb7764257,0x4bff4bd7,0xcbaccbfd,0xc487bb75,0x4bc84c00,0x43710000,0xc820c4d5,0x4adb4ba0,0x4a194b22,0x492e473d,0xcac7c99b,0x484049b5,
0x463148ba,0x4b604a74,0xcbf8cb95,0x3dc9451d,0xbc9c412e,0x4bfb4be5,0xcb6fcbeb,0xc5ebc099,0x4bc54c00,0x43a20000,0xc87fc593,0x4a9e4b80,
0x4a004b17,0x494a476a,0xcb0dc9f2,0x4790495b,0x45bc4891,0x4b784a92,0xcc00cbc0,0x317f43f7,0xbf594004,0x4bf24bf0,0xcb21cbca,0xc742c34c,
0x4bc24c00,0x43d30000,0xc8dbc64e,0x4a5c4b5a,0x49e74b0b,0x49664796,0xcb4aca43,0x469948fb,0x45464867,0x4b8e4aae,0xcbfbcbe0,0xbc6a41aa,
0xc1093db0,0x4be64bf8,0xcac4cb9b,0xc845c4f9,0x4bbf4c00,0x44020000,0xc933c705,0x4a154b30,0x49cd4aff,0x498247c2,0xcb7fca8e,0x45994896,
0x44cf483d,0x4ba14ac9,0xcbe9cbf5,0xc0be3eaa,0xc2633aac,0x4bd74bfd,0xca58cb5d,0xc8e0c642,0x4bbc4c00,0x441a0000,0xc986c7b7,0x49c94b02,
0x49b34af3,0x499d47ee,0xcbabcad3,0x4493482d,0x44574812,0x4bb34ae3,0xcbcbcbff,0xc34037da,0xc3ba33db,0x4bc34c00,0xc9dfcb11,0xc970c780,
0x4bb84c00,0x44320000,0xc9d6c832,0x49794ad0,0x49994ae6,0x49b8480d,0xcbcecb11,0x430f4780,0x43ba47cd,0x4bc34afc,0xcb9fcbfe,0xc4dbb97f,
0xc487b57f,0x4bac4c00,0xc958cab8,0xc9f4c858,0x4bb54c00,0x444b0000,0xca21c887,0x49244a99,0x497d4ad9,0x49d24822,0xcbe7cb49,0x40f0469e,
0x42c64775,0x4bd24b14,0xcb68cbf2,0xc60ebf72,0xc52fbb75,0x4b924bfd,0xc8c7ca52,0xca6bc8e7,0x4bb24c00,0x44630000,0xca67c8d8,0x48cc4a5e,
0x49624acc,0x49eb4838,0xcbf8cb79,0x3d9745b6,0x41cf471b,0x4bde4b2b,0xcb24cbdb,0xc737c20d,0xc5d4be14,0x4b734bf7,0xc82ac9e1,0xcad5c96d,
0x4bae4c00,0x447b0000,0xcaa9c927,0x486f4a1f,0x49464abf,0x4a04484d,0xcc00cba2,0x351b44c9,0x40d746c1,0x4be84b41,0xcad5cbb9,0xc82ac42c,
0xc676c036,0x4b524bee,0xc70ac964,0xcb2fc9e9,0x4bab4c00,0x44930000,0xcae5c972,0x480f49dc,0x49294ab1,0x4a1d4862,0xcbfecbc4,0xba1643ae,
0x3fbd4665,0x4bf14b55,0xca7acb8c,0xc8b2c54c,0xc715c160,0x4b2c4be3,0xc5b1c8dd,0xcb7aca5a,0x4ba74c00,0x44ab0000,0xcb1bc9ba,0x47594996,
0x490c4aa3,0x4a354877,0xcbf2cbdf,0xbf5941c3,0x3dc94608,0x4bf84b69,0xca15cb55,0xc933c665,0xc7b2c288,0x4b044bd5,0xc44bc84d,0xcbb5cabf,
0x4ba34c00,0x44c30000,0xcb4cc9fe,0x468d494d,0x48ee4a95,0x4a4d488c,0xcbdecbf1,0xc1cf3fa4,0x3ba745ab,0x4bfc4b7b,0xc9a6cb14,0xc9aac775,
0xc825c3ae,0x4ad84bc4,0xc1b6c76a,0xcbdfcb17,0x4b9f4c00,0x44db0000,0xcb78ca3f,0x45bc4900,0x48d14a87,0x4a6448a0,0xcbc0cbfd,0xc3eb3b75,
0x3776454c,0x4bff4b8c,0xc92ecac9,0xca19c83d,0xc86fc469,0x4aa94bb1,0xbd97c62b,0xcbf8cb62,0x4b9c4c00,0x44f30000,0xcb9eca7c,0x44e748b0,
0x48b24a78,0x4a7a48b5,0xcb9acc00,0xc4ffaa48,0xa64844ed,0x4c004b9d,0xc8adca74,0xca7ec8ba,0xc8b7c4f9,0x4a764b9b,0x2cb6c4e1,0xcc00cb9e,
0x4b984c00,0x450b0000,0xcbbdcab5,0x440e485d,0x48944a69,0x4a9048c9,0xcb6acbfc,0xc602bc1f,0xb81f448d,0x4bff4bab,0xc825ca17,0xcad8c930,
0xc8fdc587,0x4a414b82,0x3e2dc31b,0xcbf6cbcd,0x4b944c00,0x45230000,0xcbd7cae9,0x42634807,0x48744a5a,0x4aa548dd,0xcb32cbf0,0xc6ffc004,
0xbc06442c,0x4bfc4bb9,0xc72cc9b1,0xcb27c99f,0xc941c614,0x4a094b67,0x4201c067,0xcbdccbed,0x4b904c00,0x453a0000,0xcbeacb1a,0x40a6475e,
0x48554a4b,0x4aba48f1,0xcaf1cbdc,0xc7f3c1f4,0xbdfb4396,0x4bf74bc6,0xc602c943,0xcb6aca07,0xc982c69e,0x49cd4b49,0x446fbaac,0xcbb0cbfd,
0x4b8b4c00,0x45520000,0xcbf8cb46,0x3dc946aa,0x48354a3b,0x4ace4905,0xcaa9cbc1,0xc86fc3df,0xbfef42d2,0x4bf04bd1,0xc4cfc8ce,0xcba1ca65,
0xc9c0c726,0x49904b28,0x45d43852,0xcb73cbff,0x4b874c00,0x456a0000,0xcbffcb6e,0x388445f1,0x48154a2b,0x4ae14918,0xca58cb9e,0xc8e0c4e1,
0xc0f0420d,0x4be74bdb,0xc328c852,0xcbcccabc,0xc9fcc7ac,0x494f4b05,0x472c3fa4,0xcb27cbf1,0x4b834c00,0x45810000,0xcc00cb91,0xb51b4534,
0x47e84a1b,0x4af4492b,0xca00cb74,0xc94ac5ce,0xc1e84147,0x4bdd4be4,0xc0a6c7a1,0xcbeacb08,0xca35c817,0x490c4ae0,0x483a4288,0xcacbcbd5,
0x4b7f4c00,0x45990000,0xcbfacbaf,0xbcce4475,0x47a64a0b,0x4b07493e,0xc9a1cb43,0xc9afc6b5,0xc2de4080,0x4bd04bec,0xbc38c693,0xcbfccb4b,
0xca6bc858,0x48c74ab8,0x48d64499,0xca60cbaa,0x4b7a4c00,0x45b10000,0xcbefcbc9,0xc0294365,0x476449fa,0x4b184951,0xc93ccb0b,0xca0dc796,
0xc3d33f72,0x4bc24bf2,0x3311c57c,0xcc00cb84,0xca9ec896,0x487f4a8e,0x496645e5,0xc9e7cb70,0x4b764c00,0x45c80000,0xcbddcbdd,0xc1e841db,
0x472149e9,0x4b2a4964,0xc8d1cacc,0xca64c838,0xc4633de2,0x4bb24bf7,0x3dfbc45d,0xcbf7cbb2,0xcacec8d3,0x48354a62,0x49eb4726,0xc962cb28,
0x4b714c00,0x45df0000,0xcbc5cbed,0xc3a2404e,0x46dd49d8,0x4b3a4976,0xc85fca87,0xcab3c8a0,0xc4db3c51,0x4b9f4bfb,0x4185c26f,0xcbe1cbd6,
0xcafbc90e,0x47d24a33,0x4a64482d,0xc8d1cad3,0x4b6c4c00,0x45f70000,0xcba7cbf8,0xc4ab3d7e,0x469949c7,0x4b4a4989,0xc7d2ca3b,0xcafbc905,
0xc552397f,0x4b8b4bfe,0x4402c01d,0xcbbfcbef,0xcb24c948,0x47374a02,0x4ace48bf,0xc835ca71,0x4b684c00,0x460e0000,0xcb83cbff,0xc58138b6,
0x465449b5,0x4b59499b,0xc6ddc9e9,0xcb3ac964,0xc5c834b6,0x4b764c00,0x453abb11,0xcb90cbfd,0xcb4ac980,0x469949d0,0x4b2a4948,0xc721ca02,
0x2c002c00,0x2c002c00,0x2c002c00,0x2c002c00,0x2b642c00,0x261f29a8,0xa61f0000,0xab64a9a8,0x29a82c00,0xa9a80000,0xa9a8ac00,0x29a80000,
0x261f2c00,0xab64a9a8,0x2b640000,0xa61f29a8,0x2c00,0xac00,0x2c00,0xac00,0xa61f2c00,0x2b64a9a8,0xab640000,0x261f29a8,
0xa9a82c00,0x29a80000,0x29a8ac00,0xa9a80000,0xab642c00,0xa61f29a8,0x261f0000,0x2b64a9a8,0,0,0,0,
0x261f0000,0x2b6429a8,0x2b642c00,0x261f29a8,0x29a80000,0x29a82c00,0xa9a80000,0xa9a8ac00,0x2b640000,0xa61f29a8,0xa61fac00,0x2b6429a8,
0x2c000000,0xac000000,0x2c000000,0xac000000,0x2b640000,0xa61fa9a8,0xa61f2c00,0x2b64a9a8,0x29a80000,0x29a8ac00,0xa9a80000,0xa9a82c00,
0x261f0000,0x2b64a9a8,0x2b64ac00,0x261fa9a8,0xac002c00,0xac002c00,0xac002c00,0xac002c00,0xab642c00,0xa61f29a8,0x261f0000,0x2b64a9a8,
0xa9a82c00,0x29a80000,0x29a8ac00,0xa9a80000,0xa61f2c00,0x2b64a9a8,0xab640000,0x261f29a8,0x2c00,0xac00,0x2c00,0xac00,
0x261f2c00,0xab64a9a8,0x2b640000,0xa61f29a8,0x29a82c00,0xa9a80000,0xa9a8ac00,0x29a80000,0x2b642c00,0x261f29a8,0xa61f0000,0xab64a9a8,
0,0,0,0,0xa61f0000,0xab6429a8,0xab642c00,0xa61f29a8,0xa9a80000,0xa9a82c00,0x29a80000,0x29a8ac00,
0xab640000,0x261f29a8,0x261fac00,0xab6429a8,0xac000000,0x2c000000,0xac000000,0x2c000000,0xab640000,0x261fa9a8,0x261f2c00,0xab64a9a8,
0xa9a80000,0xa9a8ac00,0x29a80000,0x29a82c00,0xa61f0000,0xab64a9a8,0xab64ac00,0xa61fa9a8,0,0,0,0,
0xa61f0000,0xab64a9a8,0xab64ac00,0xa61fa9a8,0xa9a80000,0xa9a8ac00,0x29a80000,0x29a82c00,0xab640000,0x261fa9a8,0x261f2c00,0xab64a9a8,
0xac000000,0x2c000000,0xac000000,0x2c000000,0xab640000,0x261f29a8,0x261fac00,0xab6429a8,0xa9a80000,0xa9a82c00,0x29a80000,0x29a8ac00,
0xa61f0000,0xab6429a8,0xab642c00,0xa61f29a8,0x2c002c00,0x2c002c00,0x2c002c00,0x2c002c00,0x2b642c00,0x261f29a8,0xa61f0000,0xab64a9a8,
0x29a82c00,0xa9a80000,0xa9a8ac00,0x29a80000,0x261f2c00,0xab64a9a8,0x2b640000,0xa61f29a8,0x2c00,0xac00,0x2c00,0xac00,
0xa61f2c00,0x2b64a9a8,0xab640000,0x261f29a8,0xa9a82c00,0x29a80000,0x29a8ac00,0xa9a80000,0xab642c00,0xa61f29a8,0x261f0000,0x2b64a9a8,
0,0,0,0,0x261f0000,0x2b64a9a8,0x2b64ac00,0x261fa9a8,0x29a80000,0x29a8ac00,0xa9a80000,0xa9a82c00,
0x2b640000,0xa61fa9a8,0xa61f2c00,0x2b64a9a8,0x2c000000,0xac000000,0x2c000000,0xac000000,0x2b640000,0xa61f29a8,0xa61fac00,0x2b6429a8,
0x29a80000,0x29a82c00,0xa9a80000,0xa9a8ac00,0x261f0000,0x2b6429a8,0x2b642c00,0x261f29a8,0xac002c00,0xac002c00,0xac002c00,0xac002c00,
0xab642c00,0xa61f29a8,0x261f0000,0x2b64a9a8,0xa9a82c00,0x29a80000,0x29a8ac00,0xa9a80000,0xa61f2c00,0x2b64a9a8,0xab640000,0x261f29a8,
0x2c00,0xac00,0x2c00,0xac00,0x261f2c00,0xab64a9a8,0x2b640000,0xa61f29a8,0x29a82c00,0xa9a80000,0xa9a8ac00,0x29a80000,
0x2b642c00,0x261f29a8,0xa61f0000,0xab64a9a8,0x2c002c00,0x2c002c00,0x2c002c00,0x2c002c00,0xab64ac00,0xa61fa9a8,0x261f0000,0x2b6429a8,
0x29a82c00,0xa9a80000,0xa9a8ac00,0x29a80000,0xa61fac00,0x2b6429a8,0xab640000,0x261fa9a8,0x2c00,0xac00,0x2c00,0xac00,
0x261fac00,0xab6429a8,0x2b640000,0xa61fa9a8,0xa9a82c00,0x29a80000,0x29a8ac00,0xa9a80000,0x2b64ac00,0x261fa9a8,0xa61f0000,0xab6429a8,
0,0,0,0,0xa61f0000,0xab64a9a8,0xab64ac00,0xa61fa9a8,0x29a80000,0x29a82c00,0xa9a80000,0xa9a8ac00,
0xab640000,0x261fa9a8,0x261f2c00,0xab64a9a8,0x2c000000,0xac000000,0x2c000000,0xac000000,0xab640000,0x261f29a8,0x261fac00,0xab6429a8,
0x29a80000,0x29a8ac00,0xa9a80000,0xa9a82c00,0xa61f0000,0xab6429a8,0xab642c00,0xa61f29a8,0xac002c00,0xac002c00,0xac002c00,0xac002c00,
0x2b64ac00,0x261fa9a8,0xa61f0000,0xab6429a8,0xa9a82c00,0x29a80000,0x29a8ac00,0xa9a80000,0x261fac00,0xab6429a8,0x2b640000,0xa61fa9a8,
0x2c00,0xac00,0x2c00,0xac00,0xa61fac00,0x2b6429a8,0xab640000,0x261fa9a8,0x29a82c00,0xa9a80000,0xa9a8ac00,0x29a80000,
0xab64ac00,0xa61fa9a8,0x261f0000,0x2b6429a8,0,0,0,0,0x261f0000,0x2b64a9a8,0x2b64ac00,0x261fa9a8,
0xa9a80000,0xa9a82c00,0x29a80000,0x29a8ac00,0x2b640000,0xa61fa9a8,0xa61f2c00,0x2b64a9a8,0xac000000,0x2c000000,0xac000000,0x2c000000,
0x2b640000,0xa61f29a8,0xa61fac00,0x2b6429a8,0xa9a80000,0xa9a8ac00,0x29a80000,0x29a82c00,0x261f0000,0x2b6429a8,0x2b642c00,0x261f29a8,
0,0,0,0,0x261f0000,0x2b6429a8,0x2b642c00,0x261f29a8,0xa9a80000,0xa9a8ac00,0x29a80000,0x29a82c00,
0x2b640000,0xa61f29a8,0xa61fac00,0x2b6429a8,0xac000000,0x2c000000,0xac000000,0x2c000000,0x2b640000,0xa61fa9a8,0xa61f2c00,0x2b64a9a8,
0xa9a80000,0xa9a82c00,0x29a80000,0x29a8ac00,0x261f0000,0x2b64a9a8,0x2b64ac00,0x261fa9a8,0x2c002c00,0x2c002c00,0x2c002c00,0x2c002c00,
0xab64ac00,0xa61fa9a8,0x261f0000,0x2b6429a8,0x29a82c00,0xa9a80000,0xa9a8ac00,0x29a80000,0xa61fac00,0x2b6429a8,0xab640000,0x261fa9a8,
0x2c00,0xac00,0x2c00,0xac00,0x261fac00,0xab6429a8,0x2b640000,0xa61fa9a8,0xa9a82c00,0x29a80000,0x29a8ac00,0xa9a80000,
0x2b64ac00,0x261fa9a8,0xa61f0000,0xab6429a8,0,0,0,0,0xa61f0000,0xab6429a8,0xab642c00,0xa61f29a8,
0x29a80000,0x29a8ac00,0xa9a80000,0xa9a82c00,0xab640000,0x261f29a8,0x261fac00,0xab6429a8,0x2c000000,0xac000000,0x2c000000,0xac000000,
0xab640000,0x261fa9a8,0x261f2c00,0xab64a9a8,0x29a80000,0x29a82c00,0xa9a80000,0xa9a8ac00,0xa61f0000,0xab64a9a8,0xab64ac00,0xa61fa9a8,
0xac002c00,0xac002c00,0xac002c00,0xac002c00,0x2b64ac00,0x261fa9a8,0xa61f0000,0xab6429a8,0xa9a82c00,0x29a80000,0x29a8ac00,0xa9a80000,
0x261fac00,0xab6429a8,0x2b640000,0xa61fa9a8,0x2c00,0xac00,0x2c00,0xac00,0xa61fac00,0x2b6429a8,0xab640000,0x261fa9a8,
0x29a82c00,0xa9a80000,0xa9a8ac00,0x29a80000,0xab64ac00,0xa61fa9a8,0x261f0000,0x2b6429a8,0x2bd92c00,0x2aa72b64,0x287229a8,0x223e261f,
0x2aa72c00,0xa23e261f,0xabd9a9a8,0xa872ab64,0x28722c00,0xabd9a61f,0x223ea9a8,0x2aa72b64,0x223e2c00,0xa872ab64,0x2aa729a8,0xabd9a61f,
0xa23e2c00,0x2872ab64,0xaaa729a8,0x2bd9a61f,0xa8722c00,0x2bd9a61f,0xa23ea9a8,0xaaa72b64,0xaaa72c00,0x223e261f,0x2bd9a9a8,0x2872ab64,
0xabd92c00,0xaaa72b64,0xa87229a8,0xa23e261f,0x223e0000,0x2872261f,0x2aa729a8,0x2bd92b64,0x28720000,0x2bd92b64,0x223e29a8,0xaaa7a61f,
0x2aa70000,0x223e2b64,0xabd9a9a8,0x2872a61f,0x2bd90000,0xaaa7261f,0x2872a9a8,0xa23e2b64,0x2bd90000,0xaaa7a61f,0x287229a8,0xa23eab64,
0x2aa70000,0x223eab64,0xabd929a8,0x2872261f,0x28720000,0x2bd9ab64,0x223ea9a8,0xaaa7261f,0x223e0000,0x2872a61f,0x2aa7a9a8,0x2bd9ab64,
0xabd92c00,0xaaa72b64,0xa87229a8,0xa23e261f,0xaaa72c00,0x223e261f,0x2bd9a9a8,0x2872ab64,0xa8722c00,0x2bd9a61f,0xa23ea9a8,0xaaa72b64,
0xa23e2c00,0x2872ab64,0xaaa729a8,0x2bd9a61f,0x223e2c00,0xa872ab64,0x2aa729a8,0xabd9a61f,0x28722c00,0xabd9a61f,0x223ea9a8,0x2aa72b64,
0x2aa72c00,0xa23e261f,0xabd9a9a8,0xa872ab64,0x2bd92c00,0x2aa72b64,0x287229a8,0x223e261f,0xa23e0000,0xa872261f,0xaaa729a8,0xabd92b64,
0xa8720000,0xabd92b64,0xa23e29a8,0x2aa7a61f,0xaaa70000,0xa23e2b64,0x2bd9a9a8,0xa872a61f,0xabd90000,0x2aa7261f,0xa872a9a8,0x223e2b64,
0xabd90000,0x2aa7a61f,0xa87229a8,0x223eab64,0xaaa70000,0xa23eab64,0x2bd929a8,0xa872261f,0xa8720000,0xabd9ab64,0xa23ea9a8,0x2aa7261f,
0xa23e0000,0xa872a61f,0xaaa7a9a8,0xabd9ab64,0xa23e0000,0xa872a61f,0xaaa7a9a8,0xabd9ab64,0xa8720000,0xabd9ab64,0xa23ea9a8,0x2aa7261f,
0xaaa70000,0xa23eab64,0x2bd929a8,0xa872261f,0xabd90000,0x2aa7a61f,0xa87229a8,0x223eab64,0xabd90000,0x2aa7261f,0xa872a9a8,0x223e2b64,
0xaaa70000,0xa23e2b64,0x2bd9a9a8,0xa872a61f,0xa8720000,0xabd92b64,0xa23e29a8,0x2aa7a61f,0xa23e0000,0xa872261f,0xaaa729a8,0xabd92b64,
0x2bd92c00,0x2aa72b64,0x287229a8,0x223e261f,0x2aa72c00,0xa23e261f,0xabd9a9a8,0xa872ab64,0x28722c00,0xabd9a61f,0x223ea9a8,0x2aa72b64,
0x223e2c00,0xa872ab64,0x2aa729a8,0xabd9a61f,0xa23e2c00,0x2872ab64,0xaaa729a8,0x2bd9a61f,0xa8722c00,0x2bd9a61f,0xa23ea9a8,0xaaa72b64,
0xaaa72c00,0x223e261f,0x2bd9a9a8,0x2872ab64,0xabd92c00,0xaaa72b64,0xa87229a8,0xa23e261f,0x223e0000,0x2872a61f,0x2aa7a9a8,0x2bd9ab64,
0x28720000,0x2bd9ab64,0x223ea9a8,0xaaa7261f,0x2aa70000,0x223eab64,0xabd929a8,0x2872261f,0x2bd90000,0xaaa7a61f,0x287229a8,0xa23eab64,
0x2bd90000,0xaaa7261f,0x2872a9a8,0xa23e2b64,0x2aa70000,0x223e2b64,0xabd9a9a8,0x2872a61f,0x28720000,0x2bd92b64,0x223e29a8,0xaaa7a61f,
0x223e0000,0x2872261f,0x2aa729a8,0x2bd92b64,0xabd92c00,0xaaa72b64,0xa87229a8,0xa23e261f,0xaaa72c00,0x223e261f,0x2bd9a9a8,0x2872ab64,
0xa8722c00,0x2bd9a61f,0xa23ea9a8,0xaaa72b64,0xa23e2c00,0x2872ab64,0xaaa729a8,0x2bd9a61f,0x223e2c00,0xa872ab64,0x2aa729a8,0xabd9a61f,
0x28722c00,0xabd9a61f,0x223ea9a8,0x2aa72b64,0x2aa72c00,0xa23e261f,0xabd9a9a8,0xa872ab64,0x2bd92c00,0x2aa72b64,0x287229a8,0x223e261f,
0xa23e0000,0xa872a61f,0xaaa7a9a8,0xabd9ab64,0x28720000,0x2bd92b64,0x223e29a8,0xaaa7a61f,0xaaa70000,0xa23eab64,0x2bd929a8,0xa872261f,
0x2bd90000,0xaaa7261f,0x2872a9a8,0xa23e2b64,0xabd90000,0x2aa7261f,0xa872a9a8,0x223e2b64,0x2aa70000,0x223eab64,0xabd929a8,0x2872261f,
0xa8720000,0xabd92b64,0xa23e29a8,0x2aa7a61f,0x223e0000,0x2872a61f,0x2aa7a9a8,0x2bd9ab64,0x2bd92c00,0x2aa72b64,0x287229a8,0x223e261f,
0xaaa7ac00,0x223ea61f,0x2bd929a8,0x28722b64,0x28722c00,0xabd9a61f,0x223ea9a8,0x2aa72b64,0xa23eac00,0x28722b64,0xaaa7a9a8,0x2bd9261f,
0xa23e2c00,0x2872ab64,0xaaa729a8,0x2bd9a61f,0x2872ac00,0xabd9261f,0x223e29a8,0x2aa7ab64,0xaaa72c00,0x223e261f,0x2bd9a9a8,0x2872ab64,
0x2bd9ac00,0x2aa7ab64,0x2872a9a8,0x223ea61f,0x223e0000,0x2872a61f,0x2aa7a9a8,0x2bd9ab64,0xa8720000,0xabd92b64,0xa23e29a8,0x2aa7a61f,
0x2aa70000,0x223eab64,0xabd929a8,0x2872261f,0xabd90000,0x2aa7261f,0xa872a9a8,0x223e2b64,0x2bd90000,0xaaa7261f,0x2872a9a8,0xa23e2b64,
0xaaa70000,0xa23eab64,0x2bd929a8,0xa872261f,0x28720000,0x2bd92b64,0x223e29a8,0xaaa7a61f,0xa23e0000,0xa872a61f,0xaaa7a9a8,0xabd9ab64,
0xabd92c00,0xaaa72b64,0xa87229a8,0xa23e261f,0x2aa7ac00,0xa23ea61f,0xabd929a8,0xa8722b64,0xa8722c00,0x2bd9a61f,0xa23ea9a8,0xaaa72b64,
0x223eac00,0xa8722b64,0x2aa7a9a8,0xabd9261f,0x223e2c00,0xa872ab64,0x2aa729a8,0xabd9a61f,0xa872ac00,0x2bd9261f,0xa23e29a8,0xaaa7ab64,
0x2aa72c00,0xa23e261f,0xabd9a9a8,0xa872ab64,0xabd9ac00,0xaaa7ab64,0xa872a9a8,0xa23ea61f,0xabd9ac00,0xaaa7ab64,0xa872a9a8,0xa23ea61f,
0x2aa72c00,0xa23e261f,0xabd9a9a8,0xa872ab64,0xa872ac00,0x2bd9261f,0xa23e29a8,0xaaa7ab64,0x223e2c00,0xa872ab64,0x2aa729a8,0xabd9a61f,
0x223eac00,0xa8722b64,0x2aa7a9a8,0xabd9261f,0xa8722c00,0x2bd9a61f,0xa23ea9a8,0xaaa72b64,0x2aa7ac00,0xa23ea61f,0xabd929a8,0xa8722b64,
0xabd92c00,0xaaa72b64,0xa87229a8,0xa23e261f,0xa23e0000,0xa872a61f,0xaaa7a9a8,0xabd9ab64,0x28720000,0x2bd92b64,0x223e29a8,0xaaa7a61f,
0xaaa70000,0xa23eab64,0x2bd929a8,0xa872261f,0x2bd90000,0xaaa7261f,0x2872a9a8,0xa23e2b64,0xabd90000,0x2aa7261f,0xa872a9a8,0x223e2b64,
0x2aa70000,0x223eab64,0xabd929a8,0x2872261f,0xa8720000,0xabd92b64,0xa23e29a8,0x2aa7a61f,0x223e0000,0x2872a61f,0x2aa7a9a8,0x2bd9ab64,
0x2bd9ac00,0x2aa7ab64,0x2872a9a8,0x223ea61f,0xaaa72c00,0x223e261f,0x2bd9a9a8,0x2872ab64,0x2872ac00,0xabd9261f,0x223e29a8,0x2aa7ab64,
0xa23e2c00,0x2872ab64,0xaaa729a8,0x2bd9a61f,0xa23eac00,0x28722b64,0xaaa7a9a8,0x2bd9261f,0x28722c00,0xabd9a61f,0x223ea9a8,0x2aa72b64,
0xaaa7ac00,0x223ea61f,0x2bd929a8,0x28722b64,0x2bd92c00,0x2aa72b64,0x287229a8,0x223e261f,0x223e0000,0x2872a61f,0x2aa7a9a8,0x2bd9ab64,
0xa8720000,0xabd92b64,0xa23e29a8,0x2aa7a61f,0x2aa70000,0x223eab64,0xabd929a8,0x2872261f,0xabd90000,0x2aa7261f,0xa872a9a8,0x223e2b64,
0x2bd90000,0xaaa7261f,0x2872a9a8,0xa23e2b64,0xaaa70000,0xa23eab64,0x2bd929a8,0xa872261f,0x28720000,0x2bd92b64,0x223e29a8,0xaaa7a61f,
0xa23e0000,0xa872a61f,0xaaa7a9a8,0xabd9ab64,0x27fe2800,0x96480000,0x273b2764,0xa2d7a21f,0x27ea27f6,0x9cb29a46,0x26dd270e,0xa41da38b,
0x27c327d9,0x9fc69e3e,0x266d26a7,0xa4c4a472,0x278827a8,0xa164a0a5,0x25ed262f,0xa55fa513,0x27c32800,0x9fc60000,0xa4c4a21f,0xa66da764,
0x25ed270e,0xa55fa38b,0xa73ba62f,0xa2d7a513,0x21642472,0xa788a6a7,0xa7fea7d9,0x16489e3e,0x9cb21a46,0xa7eaa7f6,0xa6dda7a8,0x241d20a5,
0x273b2800,0xa2d70000,0xa55fa764,0x25ed221f,0x1fc62513,0xa7c3a62f,0x1cb2a0a5,0x27ea27a8,0xa4c49e3e,0xa66da7d9,0x26dd2472,0x241d26a7,
0xa7fea70e,0x9648a38b,0x278827f6,0xa1641a46,0x266d2800,0xa4c40000,0x26dd221f,0x241d2764,0xa16420a5,0xa788a7a8,0x25ed27f6,0xa55f9a46,
0xa7fea6a7,0x1648a472,0xa2d71e3e,0xa73ba7d9,0x9fc6a62f,0x27c32513,0xa7eaa70e,0x1cb2a38b,0x255f2800,0xa5ed0000,0x21642764,0xa788a21f,
0xa66d9a46,0xa4c4a7f6,0xa7c3a38b,0x9fc6a70e,0xa41da7d9,0x26dd1e3e,0x9cb2a6a7,0x27ea2472,0x273b20a5,0x22d727a8,0x27fe2513,0x1648262f,
0x241d2800,0xa6dd0000,0xa7eaa21f,0x9cb2a764,0xa7fea38b,0x9648a70e,0x2164a513,0x2788262f,0x22d7a472,0x273b26a7,0x255f27d9,0xa5ed1e3e,
0x24c427f6,0xa66d1a46,0xa7c3a0a5,0x9fc6a7a8,0x21642800,0xa7880000,0x1648a764,0x27fe221f,0xa6dda62f,0x241da513,0x24c427a8,0xa66d20a5,
0x27ea1e3e,0x1cb227d9,0xa7c3a472,0x1fc6a6a7,0xa55f238b,0xa5eda70e,0x273b9a46,0x22d727f6,0x1cb22800,0xa7ea0000,0x27c3221f,0x9fc62764,
0xa2d7a7a8,0x273ba0a5,0xa7fe9a46,0x9648a7f6,0x255f26a7,0xa5ed2472,0x27889e3e,0x216427d9,0xa6dda513,0x241da62f,0xa66d238b,0xa4c4a70e,
0x96482800,0xa7fe0000,0xa2d72764,0xa73ba21f,0x1cb2a7f6,0x27ea1a46,0x241da70e,0x26dd238b,0x9fc627d9,0xa7c39e3e,0xa4c426a7,0xa66da472,
0x2164a7a8,0x278820a5,0x255fa62f,0x25ed2513,0x9fc62800,0xa7c30000,0xa66da21f,0x24c4a764,0x255fa70e,0x25ed238b,0x22d7262f,0xa73b2513,
0xa7882472,0xa164a6a7,0x1648a7d9,0x27fe9e3e,0x27ea9a46,0x9cb227f6,0xa41d27a8,0xa6dda0a5,0xa2d72800,0xa73b0000,0x25eda764,0x255f221f,
0x27c3a513,0x1fc6262f,0xa7ea20a5,0x1cb2a7a8,0xa66d9e3e,0x24c4a7d9,0x241d2472,0xa6dd26a7,0x1648270e,0xa7fe238b,0x2164a7f6,0x27889a46,
0xa4c42800,0xa66d0000,0x241d221f,0xa6dd2764,0x2788a0a5,0xa16427a8,0x255fa7f6,0x25ed1a46,0x1648a6a7,0x27fea472,0xa73b1e3e,0x22d7a7d9,
0xa7c3262f,0x9fc6a513,0x9cb2270e,0xa7ea238b,0xa5ed2800,0xa55f0000,0xa7882764,0xa164a21f,0x24c41a46,0xa66d27f6,0x1fc6238b,0xa7c3270e,
0x26dda7d9,0x241d1e3e,0x27eaa6a7,0x1cb22472,0xa2d7a0a5,0x273ba7a8,0x9648a513,0x27fea62f,0xa6dd2800,0xa41d0000,0x9cb2a21f,0x27eaa764,
0x1648238b,0xa7fe270e,0xa7882513,0x2164a62f,0x273ba472,0xa2d726a7,0xa5ed27d9,0xa55f1e3e,0x266da7f6,0x24c49a46,0x1fc620a5,0xa7c327a8,
0xa7882800,0xa1640000,0x27fea764,0x9648221f,0xa41d262f,0xa6dd2513,0x266da7a8,0x24c4a0a5,0x1cb21e3e,0xa7ea27d9,0x1fc6a472,0x27c3a6a7,
0x25eda38b,0xa55f270e,0xa2d71a46,0x273ba7f6,0xa7ea2800,0x9cb20000,0x9fc6221f,0xa7c32764,0xa73b27a8,0xa2d720a5,0x16481a46,0xa7fe27f6,
0xa5ed26a7,0xa55f2472,0x21649e3e,0xa78827d9,0xa41d2513,0xa6dd262f,0x24c4a38b,0xa66d270e,0xa7fe2800,0x16480000,0xa73b2764,0x22d7a21f,
0xa7ea27f6,0x1cb29a46,0xa6dd270e,0x241da38b,0xa7c327d9,0x1fc69e3e,0xa66d26a7,0x24c4a472,0xa78827a8,0x2164a0a5,0xa5ed262f,0x255fa513,
0xa7c32800,0x1fc60000,0x24c4a21f,0x266da764,0xa5ed270e,0x255fa38b,0x273ba62f,0x22d7a513,0xa1642472,0x2788a6a7,0x27fea7d9,0x96489e3e,
0x1cb21a46,0x27eaa7f6,0x26dda7a8,0xa41d20a5,0xa73b2800,0x22d70000,0x255fa764,0xa5ed221f,0x9fc62513,0x27c3a62f,0x9cb2a0a5,0xa7ea27a8,
0x24c49e3e,0x266da7d9,0xa6dd2472,0xa41d26a7,0x27fea70e,0x1648a38b,0xa78827f6,0x21641a46,0xa66d2800,0x24c40000,0xa6dd221f,0xa41d2764,
0x216420a5,0x2788a7a8,0xa5ed27f6,0x255f9a46,0x27fea6a7,0x9648a472,0x22d71e3e,0x273ba7d9,0x1fc6a62f,0xa7c32513,0x27eaa70e,0x9cb2a38b,
0xa55f2800,0x25ed0000,0xa1642764,0x2788a21f,0x266d9a46,0x24c4a7f6,0x27c3a38b,0x1fc6a70e,0x241da7d9,0xa6dd1e3e,0x1cb2a6a7,0xa7ea2472,
0xa73b20a5,0xa2d727a8,0xa7fe2513,0x9648262f,0xa41d2800,0x26dd0000,0x27eaa21f,0x1cb2a764,0x27fea38b,0x1648a70e,0xa164a513,0xa788262f,
0xa2d7a472,0xa73b26a7,0xa55f27d9,0x25ed1e3e,0xa4c427f6,0x266d1a46,0x27c3a0a5,0x1fc6a7a8,0xa1642800,0x27880000,0x9648a764,0xa7fe221f,
0x26dda62f,0xa41da513,0xa4c427a8,0x266d20a5,0xa7ea1e3e,0x9cb227d9,0x27c3a472,0x9fc6a6a7,0x255f238b,0x25eda70e,0xa73b9a46,0xa2d727f6,
0x9cb22800,0x27ea0000,0xa7c3221f,0x1fc62764,0x22d7a7a8,0xa73ba0a5,0x27fe9a46,0x1648a7f6,0xa55f26a7,0x25ed2472,0xa7889e3e,0xa16427d9,
0x26dda513,0xa41da62f,0x266d238b,0x24c4a70e,0x16482800,0x27fe0000,0x22d72764,0x273ba21f,0x9cb2a7f6,0xa7ea1a46,0xa41da70e,0xa6dd238b,
0x1fc627d9,0x27c39e3e,0x24c426a7,0x266da472,0xa164a7a8,0xa78820a5,0xa55fa62f,0xa5ed2513,0x1fc62800,0x27c30000,0x266da21f,0xa4c4a764,
0xa55fa70e,0xa5ed238b,0xa2d7262f,0x273b2513,0x27882472,0x2164a6a7,0x9648a7d9,0xa7fe9e3e,0xa7ea9a46,0x1cb227f6,0x241d27a8,0x26dda0a5,
0x22d72800,0x273b0000,0xa5eda764,0xa55f221f,0xa7c3a513,0x9fc6262f,0x27ea20a5,0x9cb2a7a8,0x266d9e3e,0xa4c4a7d9,0xa41d2472,0x26dd26a7,
0x9648270e,0x27fe238b,0xa164a7f6,0xa7889a46,0x24c42800,0x266d0000,0xa41d221f,0x26dd2764,0xa788a0a5,0x216427a8,0xa55fa7f6,0xa5ed1a46,
0x9648a6a7,0xa7fea472,0x273b1e3e,0xa2d7a7d9,0x27c3262f,0x1fc6a513,0x1cb2270e,0x27ea238b,0x25ed2800,0x255f0000,0x27882764,0x2164a21f,
0xa4c41a46,0x266d27f6,0x9fc6238b,0x27c3270e,0xa6dda7d9,0xa41d1e3e,0xa7eaa6a7,0x9cb22472,0x22d7a0a5,0xa73ba7a8,0x1648a513,0xa7fea62f,
0x26dd2800,0x241d0000,0x1cb2a21f,0xa7eaa764,0x9648238b,0x27fe270e,0x27882513,0xa164a62f,0xa73ba472,0x22d726a7,0x25ed27d9,0x255f1e3e,
0xa66da7f6,0xa4c49a46,0x9fc620a5,0x27c327a8,0x27882800,0x21640000,0xa7fea764,0x1648221f,0x241d262f,0x26dd2513,0xa66da7a8,0xa4c4a0a5,
0x9cb21e3e,0x27ea27d9,0x9fc6a472,0xa7c3a6a7,0xa5eda38b,0x255f270e,0x22d71a46,0xa73ba7f6,0x27ea2800,0x1cb20000,0x1fc6221f,0x27c32764,
0x273b27a8,0x22d720a5,0x96481a46,0x27fe27f6,0x25ed26a7,0x255f2472,0xa1649e3e,0x278827d9,0x241d2513,0x26dd262f,0xa4c4a38b,0x266d270e,
0x255f25a8,0xa5eda5a8,0x2164221f,0xa788a764,0x24c42513,0xa66da62f,0x1fc620a5,0xa7c3a7a8,0x241d2472,0xa6dda6a7,0x1cb21e3e,0xa7eaa7d9,
0x22d7238b,0xa73ba70e,0x16481a46,0xa7fea7f6,0xa41da5a8,0x26dd25a8,0x27ea2764,0x1cb2221f,0x9648a0a5,0x27fe27a8,0x278827f6,0xa1649a46,
0x22d71e3e,0x273b27d9,0x255f26a7,0xa5eda472,0x266d2513,0x24c4262f,0x1fc6238b,0xa7c3a70e,0x216425a8,0xa788a5a8,0x1648a21f,0x27fe2764,
0xa41d9a46,0xa6dda7f6,0x266d238b,0x24c4270e,0xa7eaa6a7,0x9cb2a472,0x27c327d9,0x9fc61e3e,0xa5eda7a8,0x255f20a5,0x22d7262f,0xa73ba513,
0x9cb2a5a8,0x27ea25a8,0xa7c3a764,0x1fc6a21f,0x273b238b,0x22d7270e,0x9648a513,0x27fe262f,0x255f27d9,0xa5ed9e3e,0x27882472,0x216426a7,
0xa41d1a46,0xa6dda7f6,0x24c427a8,0xa66da0a5,0x964825a8,0xa7fea5a8,0xa2d7221f,0xa73ba764,0xa7eaa62f,0x1cb2a513,0xa6dda7a8,0x241da0a5,
0x1fc6a472,0x27c326a7,0x24c49e3e,0x266d27d9,0x2788270e,0xa164238b,0x25ed27f6,0xa55f1a46,0x1fc6a5a8,0x27c325a8,0x266d2764,0xa4c4221f,
0x25ed27a8,0xa55f20a5,0xa73b9a46,0xa2d7a7f6,0xa7889e3e,0xa164a7d9,0x1648a6a7,0x27fe2472,0x1cb2a62f,0x27ea2513,0x26dd270e,0xa41d238b,
0xa2d725a8,0xa73ba5a8,0x25eda21f,0x255f2764,0x9fc6a7f6,0x27c31a46,0x9cb2270e,0xa7eaa38b,0x266d26a7,0xa4c42472,0xa41da7d9,0x26dd9e3e,
0xa7fea0a5,0x9648a7a8,0x27882513,0xa164262f,0x24c4a5a8,0x266d25a8,0xa41da764,0x26dda21f,0xa164270e,0xa788a38b,0x25ed262f,0xa55f2513,
0x1648a7d9,0x27fe1e3e,0xa73ba472,0x22d7a6a7,0x1fc627f6,0xa7c31a46,0x27ea20a5,0x9cb227a8,0xa5ed25a8,0xa55fa5a8,0xa788221f,0xa164a764,
0x266da513,0x24c4262f,0x27c3a0a5,0x1fc627a8,0xa6dd2472,0xa41da6a7,0xa7ea1e3e,0x9cb2a7d9,0x273ba38b,0x22d7270e,0x27fe9a46,0x164827f6,
0x26dda5a8,0x241d25a8,0x1cb22764,0xa7ea221f,0xa7fe20a5,0x9648a7a8,0x2164a7f6,0x27881a46,0x273b1e3e,0xa2d727d9,0xa5ed26a7,0xa55fa472,
0xa4c4a513,0x266da62f,0x27c3a38b,0x1fc6270e,0xa78825a8,0xa164a5a8,0x27fea21f,0x96482764,0x26dd1a46,0xa41d27f6,0xa4c4a38b,0x266da70e,
0x9cb2a6a7,0x27eaa472,0x9fc627d9,0xa7c31e3e,0xa55f27a8,0xa5eda0a5,0x273ba62f,0x22d72513,0x27eaa5a8,0x1cb225a8,0x1fc6a764,0x27c3a21f,
0xa2d7a38b,0x273ba70e,0xa7fe2513,0x9648a62f,0xa5ed27d9,0xa55f9e3e,0x21642472,0xa78826a7,0x26dd9a46,0xa41d27f6,0x266da7a8,0x24c420a5,
0xa7fe25a8,0x1648a5a8,0xa73b221f,0x22d7a764,0x9cb2262f,0xa7ea2513,0xa41d27a8,0xa6dd20a5,0x27c3a472,0x9fc626a7,0x266d9e3e,0xa4c427d9,
0x2164a70e,0x2788a38b,0x255fa7f6,0x25ed9a46,0x27c3a5a8,0x9fc625a8,0xa4c42764,0xa66d221f,0x255fa7a8,0x25eda0a5,0x22d71a46,0xa73b27f6,
0xa1649e3e,0x2788a7d9,0x27fea6a7,0x96482472,0xa7ea262f,0x1cb2a513,0x241da70e,0x26dda38b,0xa73b25a8,0x22d7a5a8,0x255fa21f,0xa5ed2764,
0xa7c327f6,0x9fc69a46,0x27eaa70e,0x9cb2238b,0xa4c426a7,0xa66d2472,0x26dda7d9,0x241d9e3e,0x164820a5,0xa7fe27a8,0x2164a513,0x2788a62f,
0x266da5a8,0xa4c425a8,0x26dda764,0x241da21f,0x2788a70e,0xa164238b,0x255fa62f,0x25eda513,0x27fea7d9,0x96481e3e,0x22d7a472,0x273ba6a7,
0x27c3a7f6,0x1fc69a46,0x1cb2a0a5,0x27eaa7a8,0xa55f25a8,0x25eda5a8,0xa164221f,0x2788a764,0xa4c42513,0x266da62f,0x9fc620a5,0x27c3a7a8,
0xa41d2472,0x26dda6a7,0x9cb21e3e,0x27eaa7d9,0xa2d7238b,0x273ba70e,0x96481a46,0x27fea7f6,0x241da5a8,0xa6dd25a8,0xa7ea2764,0x9cb2221f,
0x1648a0a5,0xa7fe27a8,0xa78827f6,0x21649a46,0xa2d71e3e,0xa73b27d9,0xa55f26a7,0x25eda472,0xa66d2513,0xa4c4262f,0x9fc6238b,0x27c3a70e,
0xa16425a8,0x2788a5a8,0x9648a21f,0xa7fe2764,0x241d9a46,0x26dda7f6,0xa66d238b,0xa4c4270e,0x27eaa6a7,0x1cb2a472,0xa7c327d9,0x1fc61e3e,
0x25eda7a8,0xa55f20a5,0xa2d7262f,0x273ba513,0x1cb2a5a8,0xa7ea25a8,0x27c3a764,0x9fc6a21f,0xa73b238b,0xa2d7270e,0x1648a513,0xa7fe262f,
0xa55f27d9,0x25ed9e3e,0xa7882472,0xa16426a7,0x241d1a46,0x26dda7f6,0xa4c427a8,0x266da0a5,0x164825a8,0x27fea5a8,0x22d7221f,0x273ba764,
0x27eaa62f,0x9cb2a513,0x26dda7a8,0xa41da0a5,0x9fc6a472,0xa7c326a7,0xa4c49e3e,0xa66d27d9,0xa788270e,0x2164238b,0xa5ed27f6,0x255f1a46,
0x9fc6a5a8,0xa7c325a8,0xa66d2764,0x24c4221f,0xa5ed27a8,0x255f20a5,0x273b9a46,0x22d7a7f6,0x27889e3e,0x2164a7d9,0x9648a6a7,0xa7fe2472,
0x9cb2a62f,0xa7ea2513,0xa6dd270e,0x241d238b,0x22d725a8,0x273ba5a8,0xa5eda21f,0xa55f2764,0x1fc6a7f6,0xa7c31a46,0x1cb2270e,0x27eaa38b,
0xa66d26a7,0x24c42472,0x241da7d9,0xa6dd9e3e,0x27fea0a5,0x1648a7a8,0xa7882513,0x2164262f,0xa4c4a5a8,0xa66d25a8,0x241da764,0xa6dda21f,
0x2164270e,0x2788a38b,0xa5ed262f,0x255f2513,0x9648a7d9,0xa7fe1e3e,0x273ba472,0xa2d7a6a7,0x9fc627f6,0x27c31a46,0xa7ea20a5,0x1cb227a8,
0x25ed25a8,0x255fa5a8,0x2788221f,0x2164a764,0xa66da513,0xa4c4262f,0xa7c3a0a5,0x9fc627a8,0x26dd2472,0x241da6a7,0x27ea1e3e,0x1cb2a7d9,
0xa73ba38b,0xa2d7270e,0xa7fe9a46,0x964827f6,0xa6dda5a8,0xa41d25a8,0x9cb22764,0x27ea221f,0x27fe20a5,0x1648a7a8,0xa164a7f6,0xa7881a46,
0xa73b1e3e,0x22d727d9,0x25ed26a7,0x255fa472,0x24c4a513,0xa66da62f,0xa7c3a38b,0x9fc6270e,0x278825a8,0x2164a5a8,0xa7fea21f,0x16482764,
0xa6dd1a46,0x241d27f6,0x24c4a38b,0xa66da70e,0x1cb2a6a7,0xa7eaa472,0x1fc627d9,0x27c31e3e,0x255f27a8,0x25eda0a5,0xa73ba62f,0xa2d72513,
0xa7eaa5a8,0x9cb225a8,0x9fc6a764,0xa7c3a21f,0x22d7a38b,0xa73ba70e,0x27fe2513,0x1648a62f,0x25ed27d9,0x255f9e3e,0xa1642472,0x278826a7,
0xa6dd9a46,0x241d27f6,0xa66da7a8,0xa4c420a5,0x27fe25a8,0x9648a5a8,0x273b221f,0xa2d7a764,0x1cb2262f,0x27ea2513,0x241d27a8,0x26dd20a5,
0xa7c3a472,0x1fc626a7,0xa66d9e3e,0x24c427d9,0xa164a70e,0xa788a38b,0xa55fa7f6,0xa5ed9a46,0xa7c3a5a8,0x1fc625a8,0x24c42764,0x266d221f,
0xa55fa7a8,0xa5eda0a5,0xa2d71a46,0x273b27f6,0x21649e3e,0xa788a7d9,0xa7fea6a7,0x16482472,0x27ea262f,0x9cb2a513,0xa41da70e,0xa6dda38b,
0x273b25a8,0xa2d7a5a8,0xa55fa21f,0x25ed2764,0x27c327f6,0x1fc69a46,0xa7eaa70e,0x1cb2238b,0x24c426a7,0x266d2472,0xa6dda7d9,0xa41d9e3e,
0x964820a5,0x27fe27a8,0xa164a513,0xa788a62f,0xa66da5a8,0x24c425a8,0xa6dda764,0xa41da21f,0xa788a70e,0x2164238b,0xa55fa62f,0xa5eda513,
0xa7fea7d9,0x16481e3e,0xa2d7a472,0xa73ba6a7,0xa7c3a7f6,0x9fc69a46,0x9cb2a0a5,0xa7eaa7a8,
};

#define PROF(slot) do {} while (0)
#define PROF3(slot) do {} while (0)
#define PROF2(slot) do {} while (0)

__device__ __forceinline__ uint32_t smem_u32(const void* p) { return (uint32_t)__cvta_generic_to_shared(p); }

__device__ __forceinline__ void mbar_init(uint32_t a, uint32_t c) {
  asm volatile("mbarrier.init.shared::cta.b64 [%0], %1;\n" ::"r"(a), "r"(c) : "memory");
}
__device__ __forceinline__ void mbar_expect_tx(uint32_t a, uint32_t bytes) {
  asm volatile("mbarrier.arrive.expect_tx.shared::cta.b64 _, [%0], %1;\n" ::"r"(a), "r"(bytes) : "memory");
}
__device__ __forceinline__ void mbar_arrive_cluster(uint32_t cluster_addr) {
  asm volatile("mbarrier.arrive.shared::cluster.b64 _, [%0];\n" ::"r"(cluster_addr) : "memory");
}
__device__ __forceinline__ void mbar_arrive_cluster_n(uint32_t cluster_addr, uint32_t n) {
  asm volatile("mbarrier.arrive.shared::cluster.b64 _, [%0], %1;\n" ::"r"(cluster_addr), "r"(n) : "memory");
}
__device__ __forceinline__ bool mbar_try(uint32_t a, uint32_t parity) {
  uint32_t ok;
  asm volatile("{\n.reg .pred p;\nmbarrier.try_wait.parity.shared::cta.b64 p, [%1], %2;\nselp.u32 %0, 1, 0, p;\n}\n"
               : "=r"(ok) : "r"(a), "r"(parity) : "memory");
  return ok;
}
__device__ __forceinline__ void mbar_wait(uint32_t a, uint32_t parity) {
  if (mbar_try(a, parity)) return;
#pragma unroll 1
  for (int n = 0; n < SPIN_LIMIT; n++)
    if (mbar_try(a, parity)) break;
}
__device__ __forceinline__ void mbar_wait_idle(uint32_t a, uint32_t parity) {
#pragma unroll 1
  for (int n = 0; n < SPIN_LIMIT; n++) {
    uint32_t ok;
    asm volatile("{\n.reg .pred p;\nmbarrier.try_wait.parity.shared::cta.b64 p, [%1], %2, %3;\nselp.u32 %0, 1, 0, p;\n}\n"
                 : "=r"(ok) : "r"(a), "r"(parity), "r"(4000) : "memory");
    if (ok) break;
  }
}
__device__ __forceinline__ bool elect_one() {
  uint32_t p;
  asm volatile("{\n.reg .pred P;\nelect.sync _|P, 0xffffffff;\nselp.u32 %0, 1, 0, P;\n}\n" : "=r"(p));
  return p;
}
__device__ __forceinline__ uint32_t mapa(uint32_t a, uint32_t rank) {
  uint32_t r;
  asm volatile("mapa.shared::cluster.u32 %0, %1, %2;\n" : "=r"(r) : "r"(a), "r"(rank));
  return r;
}
__device__ __forceinline__ void nb_sync(int id, int n) { asm volatile("bar.sync %0, %1;\n" ::"r"(id), "r"(n) : "memory"); }
__device__ __forceinline__ void nb_arrive(int id, int n) { asm volatile("bar.arrive %0, %1;\n" ::"r"(id), "r"(n) : "memory"); }
__device__ __forceinline__ void cluster_sync_all() {
  asm volatile("barrier.cluster.arrive.relaxed.aligned;\nbarrier.cluster.wait.aligned;\n" ::: "memory");
}
__device__ __forceinline__ void fence_async_smem() { asm volatile("fence.proxy.async.shared::cta;\n" ::: "memory"); }
__device__ __forceinline__ void fence_async_all() { asm volatile("fence.proxy.async.global;\n" ::: "memory"); }

__device__ __forceinline__ void tma_load_3d(uint32_t dst, const CUtensorMap* tm, uint32_t bar, int c0, int c1, int c2) {
  asm volatile(
      "cp.async.bulk.tensor.3d.shared::cluster.global.mbarrier::complete_tx::bytes [%0], [%1, {%3, %4, %5}], [%2];\n"
      ::"r"(dst), "l"(tm), "r"(bar), "r"(c0), "r"(c1), "r"(c2) : "memory");
}
__device__ __forceinline__ void tma_load_4d(uint32_t dst, const CUtensorMap* tm, uint32_t bar, int c0, int c1, int c2, int c3) {
  asm volatile(
      "cp.async.bulk.tensor.4d.shared::cluster.global.mbarrier::complete_tx::bytes [%0], [%1, {%3, %4, %5, %6}], [%2];\n"
      ::"r"(dst), "l"(tm), "r"(bar), "r"(c0), "r"(c1), "r"(c2), "r"(c3) : "memory");
}
__device__ __forceinline__ void tma_load_3d_mc(uint32_t dst, const CUtensorMap* tm, uint32_t bar, int c0, int c1, int c2) {
  asm volatile(
      "cp.async.bulk.tensor.3d.shared::cluster.global.mbarrier::complete_tx::bytes.multicast::cluster [%0], [%1, {%3, %4, %5}], [%2], %6;\n"
      ::"r"(dst), "l"(tm), "r"(bar), "r"(c0), "r"(c1), "r"(c2), "h"((uint16_t)3) : "memory");
}
__device__ __forceinline__ void tma_load_5d(uint32_t dst, const CUtensorMap* tm, uint32_t bar, int c0, int c4) {
  asm volatile(
      "cp.async.bulk.tensor.5d.shared::cluster.global.mbarrier::complete_tx::bytes [%0], [%1, {%3, %5, %5, %5, %4}], [%2];\n"
      ::"r"(dst), "l"(tm), "r"(bar), "r"(c0), "r"(c4), "r"(0) : "memory");
}
__device__ __forceinline__ void bulk_load(uint32_t dst, const void* src, uint32_t bytes, uint32_t bar) {
  asm volatile("cp.async.bulk.shared::cluster.global.mbarrier::complete_tx::bytes [%0], [%1], %2, [%3];\n"
               ::"r"(dst), "l"(src), "r"(bytes), "r"(bar) : "memory");
}
__device__ __forceinline__ void bulk_commit() { asm volatile("cp.async.bulk.commit_group;\n" ::: "memory"); }
__device__ __forceinline__ void bulk_wait0() { asm volatile("cp.async.bulk.wait_group 0;\n" ::: "memory"); }
__device__ __forceinline__ void prefetch_tmap(const CUtensorMap* tm) {
  asm volatile("prefetch.tensormap [%0];\n" ::"l"(tm) : "memory");
}

__device__ __forceinline__ void wg_fence() { asm volatile("wgmma.fence.sync.aligned;\n" ::: "memory"); }
__device__ __forceinline__ void wg_commit() { asm volatile("wgmma.commit_group.sync.aligned;\n" ::: "memory"); }
template <int N> __device__ __forceinline__ void wg_wait() {
  asm volatile("wgmma.wait_group.sync.aligned %0;\n" ::"n"(N) : "memory");
}
__device__ __forceinline__ uint64_t mkdesc(uint32_t addr, uint32_t lbo, uint32_t sbo, uint32_t swz) {
  return (uint64_t)((addr & 0x3FFFF) >> 4) | ((uint64_t)(lbo >> 4) << 16) | ((uint64_t)(sbo >> 4) << 32) |
         ((uint64_t)swz << 62);
}

#define R4(d, o) "+f"(d[o + 0]), "+f"(d[o + 1]), "+f"(d[o + 2]), "+f"(d[o + 3])
#define R8(d, o) R4(d, o), R4(d, o + 4)
#define R16(d, o) R8(d, o), R8(d, o + 8)
#define R32(d, o) R16(d, o), R16(d, o + 16)
#define R64(d, o) R32(d, o), R32(d, o + 32)

__device__ __forceinline__ void wgmma_n192(float (&d)[96], uint64_t da, uint64_t db, uint32_t acc) {
  asm volatile(
      "{\n.reg .pred p;\nsetp.ne.u32 p, %98, 0;\n"
      "wgmma.mma_async.sync.aligned.m64n192k16.f32.bf16.bf16 "
      "{%0,%1,%2,%3,%4,%5,%6,%7,%8,%9,%10,%11,%12,%13,%14,%15,%16,%17,%18,%19,%20,%21,%22,%23,%24,%25,%26,%27,%28,%29,%30,%31,"
      "%32,%33,%34,%35,%36,%37,%38,%39,%40,%41,%42,%43,%44,%45,%46,%47,%48,%49,%50,%51,%52,%53,%54,%55,%56,%57,%58,%59,%60,%61,%62,%63,"
      "%64,%65,%66,%67,%68,%69,%70,%71,%72,%73,%74,%75,%76,%77,%78,%79,%80,%81,%82,%83,%84,%85,%86,%87,%88,%89,%90,%91,%92,%93,%94,%95}, "
      "%96, %97, p, 1, 1, 0, 1;\n}\n"
      : R64(d, 0), R32(d, 64)
      : "l"(da), "l"(db), "r"(acc));
}
__device__ __forceinline__ void wgmma_n128(float (&d)[64], uint64_t da, uint64_t db, uint32_t acc) {
  asm volatile(
      "{\n.reg .pred p;\nsetp.ne.u32 p, %66, 0;\n"
      "wgmma.mma_async.sync.aligned.m64n128k16.f32.bf16.bf16 "
      "{%0,%1,%2,%3,%4,%5,%6,%7,%8,%9,%10,%11,%12,%13,%14,%15,%16,%17,%18,%19,%20,%21,%22,%23,%24,%25,%26,%27,%28,%29,%30,%31,"
      "%32,%33,%34,%35,%36,%37,%38,%39,%40,%41,%42,%43,%44,%45,%46,%47,%48,%49,%50,%51,%52,%53,%54,%55,%56,%57,%58,%59,%60,%61,%62,%63}, "
      "%64, %65, p, 1, 1, 0, 1;\n}\n"
      : R64(d, 0)
      : "l"(da), "l"(db), "r"(acc));
}
template <int N> __device__ __forceinline__ void fence_regs(float (&d)[N]) {
#pragma unroll
  for (int i = 0; i < N; i++) asm volatile("" : "+f"(d[i])::"memory");
}

__device__ __forceinline__ void mma16816(float (&d)[4], uint32_t a0, uint32_t a1, uint32_t a2, uint32_t a3, uint32_t b0,
                                         uint32_t b1) {
  asm("mma.sync.aligned.m16n8k16.row.col.f32.bf16.bf16.f32 {%0,%1,%2,%3}, {%4,%5,%6,%7}, {%8,%9}, {%0,%1,%2,%3};\n"
      : "+f"(d[0]), "+f"(d[1]), "+f"(d[2]), "+f"(d[3])
      : "r"(a0), "r"(a1), "r"(a2), "r"(a3), "r"(b0), "r"(b1));
}
__device__ __forceinline__ void mma16816_z(float (&d)[4], uint32_t a0, uint32_t a1, uint32_t a2, uint32_t a3, uint32_t b0,
                                           uint32_t b1) {
  asm("mma.sync.aligned.m16n8k16.row.col.f32.bf16.bf16.f32 {%0,%1,%2,%3}, {%4,%5,%6,%7}, {%8,%9}, {%10,%10,%10,%10};\n"
      : "=f"(d[0]), "=f"(d[1]), "=f"(d[2]), "=f"(d[3])
      : "r"(a0), "r"(a1), "r"(a2), "r"(a3), "r"(b0), "r"(b1), "f"(0.f));
}
__device__ __forceinline__ void ldsm4t(uint32_t (&r)[4], uint32_t a) {
  asm volatile("ldmatrix.sync.aligned.m8n8.x4.trans.shared.b16 {%0,%1,%2,%3}, [%4];\n"
               : "=r"(r[0]), "=r"(r[1]), "=r"(r[2]), "=r"(r[3]) : "r"(a) : "memory");
}
__device__ __forceinline__ void ldsm2t(uint32_t& r0, uint32_t& r1, uint32_t a) {
  asm volatile("ldmatrix.sync.aligned.m8n8.x2.trans.shared.b16 {%0,%1}, [%2];\n" : "=r"(r0), "=r"(r1) : "r"(a) : "memory");
}
__device__ __forceinline__ void st_async128(uint32_t a, uint32_t bar, uint32_t x, uint32_t y, uint32_t z, uint32_t w) {
  asm volatile("st.async.weak.shared::cluster.mbarrier::complete_tx::bytes.v4.b32 [%0], {%2,%3,%4,%5}, [%1];\n"
               ::"r"(a), "r"(bar), "r"(x), "r"(y), "r"(z), "r"(w) : "memory");
}
__device__ __forceinline__ void mbar_arrive(uint32_t a) {
  asm volatile("mbarrier.arrive.shared::cta.b64 _, [%0];\n" ::"r"(a) : "memory");
}
__device__ __forceinline__ void stsm4(uint32_t a, uint32_t r0, uint32_t r1, uint32_t r2, uint32_t r3) {
  asm volatile("stmatrix.sync.aligned.m8n8.x4.shared.b16 [%0], {%1,%2,%3,%4};\n"
               ::"r"(a), "r"(r0), "r"(r1), "r"(r2), "r"(r3) : "memory");
}
__device__ __forceinline__ void stsm4t(uint32_t a, uint32_t r0, uint32_t r1, uint32_t r2, uint32_t r3) {
  asm volatile("stmatrix.sync.aligned.m8n8.x4.trans.shared.b16 [%0], {%1,%2,%3,%4};\n"
               ::"r"(a), "r"(r0), "r"(r1), "r"(r2), "r"(r3) : "memory");
}
__device__ __forceinline__ uint2 lds64(uint32_t a) {
  uint2 v;
  asm volatile("ld.shared.v2.u32 {%0,%1}, [%2];\n" : "=r"(v.x), "=r"(v.y) : "r"(a));
  return v;
}
__device__ __forceinline__ uint4 lds128(uint32_t a) {
  uint4 v;
  asm volatile("ld.shared.v4.u32 {%0,%1,%2,%3}, [%4];\n" : "=r"(v.x), "=r"(v.y), "=r"(v.z), "=r"(v.w) : "r"(a) : "memory");
  return v;
}
__device__ __forceinline__ void sts128(uint32_t a, uint32_t x, uint32_t y, uint32_t z, uint32_t w) {
  asm volatile("st.shared.v4.u32 [%0], {%1,%2,%3,%4};\n" ::"r"(a), "r"(x), "r"(y), "r"(z), "r"(w) : "memory");
}
__device__ __forceinline__ uint32_t pack_bf16(float lo, float hi) {
  uint32_t r;
  asm("cvt.rn.bf16x2.f32 %0, %1, %2;\n" : "=r"(r) : "f"(hi), "f"(lo));
  return r;
}
__device__ __forceinline__ uint32_t bmul2(uint32_t a, uint32_t b) {
  uint32_t r;
  asm("mul.rn.bf16x2 %0, %1, %2;\n" : "=r"(r) : "r"(a), "r"(b));
  return r;
}
__device__ __forceinline__ uint32_t bmax2(uint32_t a, uint32_t b) {
  uint32_t r;
  asm("max.bf16x2 %0, %1, %2;\n" : "=r"(r) : "r"(a), "r"(b));
  return r;
}
__device__ __forceinline__ uint32_t bfma2(uint32_t a, uint32_t b, uint32_t c) {
  uint32_t r;
  asm("fma.rn.bf16x2 %0, %1, %2, %3;\n" : "=r"(r) : "r"(a), "r"(b), "r"(c));
  return r;
}
__device__ __forceinline__ uint32_t badd2(uint32_t a, uint32_t b) {
  uint32_t r;
  asm("add.rn.bf16x2 %0, %1, %2;\n" : "=r"(r) : "r"(a), "r"(b));
  return r;
}
__device__ __forceinline__ void prefetch_l2(const void* p) { asm volatile("prefetch.global.L2 [%0];\n" ::"l"(p)); }
__device__ __forceinline__ void cp_async16n(uint32_t dst, const void* src) {
  asm volatile("cp.async.cg.shared.global [%0], [%1], 16;\n" ::"r"(dst), "l"(src) : "memory");
}
__device__ __forceinline__ void cp_async16(uint32_t dst, const void* src, uint32_t srcbytes) {
  asm volatile("cp.async.cg.shared.global.L2::256B [%0], [%1], 16, %2;\n" ::"r"(dst), "l"(src), "r"(srcbytes) : "memory");
}
__device__ __forceinline__ uint32_t ld_acquire(const uint32_t* p) {
  uint32_t v;
  asm volatile("ld.acquire.gpu.global.u32 %0, [%1];\n" : "=r"(v) : "l"(p) : "memory");
  return v;
}
__device__ __forceinline__ uint32_t ld_relaxed(const uint32_t* p) {
  uint32_t v;
  asm volatile("ld.relaxed.gpu.global.u32 %0, [%1];\n" : "=r"(v) : "l"(p) : "memory");
  return v;
}
__device__ __forceinline__ void st_release(uint32_t* p, uint32_t v) {
  asm volatile("st.release.gpu.global.u32 [%0], %1;\n" ::"l"(p), "r"(v) : "memory");
}
__device__ __forceinline__ void wait_flag(const uint32_t* p, uint32_t want) {
  int n = 0;
  while (ld_relaxed(p) != want && ++n < SPIN_LIMIT) __nanosleep(40);
  (void)ld_acquire(p);
}

struct Params {
  const __nv_bfloat16* x;
  const __nv_bfloat16* w;
  const __nv_bfloat16* q;
  const __nv_bfloat16* k;
  const __nv_bfloat16* v;
  const __nv_bfloat16* shift_k;
  const __nv_bfloat16* ssm_k;
  const __nv_bfloat16* ssm_D;
  const __nv_bfloat16* wo;
  __nv_bfloat16* out;
};

__device__ __forceinline__ uint32_t lds32(uint32_t a) {
  uint32_t v;
  asm volatile("ld.shared.u32 %0, [%1];\n" : "=r"(v) : "r"(a));
  return v;
}
#define W4(d, o) "=f"(d[o + 0]), "=f"(d[o + 1]), "=f"(d[o + 2]), "=f"(d[o + 3])
#define W8(d, o) W4(d, o), W4(d, o + 4)
#define W16(d, o) W8(d, o), W8(d, o + 8)
#define U4(c, d, o) c(d[o + 0]), c(d[o + 1]), c(d[o + 2]), c(d[o + 3])
#define U8(c, d, o) U4(c, d, o), U4(c, d, o + 4)
#define U16(c, d, o) U8(c, d, o), U8(c, d, o + 8)
#define U32(c, d, o) U16(c, d, o), U16(c, d, o + 16)
#define D32 "{%0,%1,%2,%3,%4,%5,%6,%7,%8,%9,%10,%11,%12,%13,%14,%15,%16,%17,%18,%19,%20,%21,%22,%23,%24,%25,%26,%27,%28,%29,%30,%31}"
#define D16 "{%0,%1,%2,%3,%4,%5,%6,%7,%8,%9,%10,%11,%12,%13,%14,%15}"
#define D8 "{%0,%1,%2,%3,%4,%5,%6,%7}"
template <int ACC> __device__ __forceinline__ void hmma_n128t(uint32_t (&d)[32], const uint32_t (&a)[4], uint64_t db) {
  if (ACC)
    asm volatile("wgmma.mma_async.sync.aligned.m64n128k16.f16.f16.f16 " D32 ", {%32,%33,%34,%35}, %36, 1, 1, 1, 1;\n"
                 : U32("+r", d, 0) : "r"(a[0]), "r"(a[1]), "r"(a[2]), "r"(a[3]), "l"(db));
  else
    asm volatile("wgmma.mma_async.sync.aligned.m64n128k16.f16.f16.f16 " D32 ", {%32,%33,%34,%35}, %36, 0, 1, 1, 1;\n"
                 : U32("=r", d, 0) : "r"(a[0]), "r"(a[1]), "r"(a[2]), "r"(a[3]), "l"(db));
}
template <int ACC, int TB> __device__ __forceinline__ void hmma_n32(uint32_t (&d)[8], const uint32_t (&a)[4], uint64_t db) {
  if (ACC)
    asm volatile("wgmma.mma_async.sync.aligned.m64n32k16.f16.f16.f16 " D8 ", {%8,%9,%10,%11}, %12, 1, 1, 1, %13;\n"
                 : U8("+r", d, 0) : "r"(a[0]), "r"(a[1]), "r"(a[2]), "r"(a[3]), "l"(db), "n"(TB));
  else
    asm volatile("wgmma.mma_async.sync.aligned.m64n32k16.f16.f16.f16 " D8 ", {%8,%9,%10,%11}, %12, 0, 1, 1, %13;\n"
                 : U8("=r", d, 0) : "r"(a[0]), "r"(a[1]), "r"(a[2]), "r"(a[3]), "l"(db), "n"(TB));
}
template <int ACC> __device__ __forceinline__ void fmma_n32t(float (&d)[16], const uint32_t (&a)[4], uint64_t db) {
  if (ACC)
    asm volatile("wgmma.mma_async.sync.aligned.m64n32k16.f32.f16.f16 " D16 ", {%16,%17,%18,%19}, %20, 1, 1, 1, 1;\n"
                 : R16(d, 0) : "r"(a[0]), "r"(a[1]), "r"(a[2]), "r"(a[3]), "l"(db));
  else
    asm volatile("wgmma.mma_async.sync.aligned.m64n32k16.f32.f16.f16 " D16 ", {%16,%17,%18,%19}, %20, 0, 1, 1, 1;\n"
                 : W16(d, 0) : "r"(a[0]), "r"(a[1]), "r"(a[2]), "r"(a[3]), "l"(db));
}
template <int N> __device__ __forceinline__ void fence_regs(uint32_t (&d)[N]) {
#pragma unroll
  for (int i = 0; i < N; i++) asm volatile("" : "+r"(d[i])::"memory");
}
__device__ __forceinline__ uint32_t hmul(uint32_t a, uint32_t b) { uint32_t r; asm("mul.rn.f16x2 %0, %1, %2;\n" : "=r"(r) : "r"(a), "r"(b)); return r; }
__device__ __forceinline__ uint32_t hadd(uint32_t a, uint32_t b) { uint32_t r; asm("add.rn.f16x2 %0, %1, %2;\n" : "=r"(r) : "r"(a), "r"(b)); return r; }
__device__ __forceinline__ uint32_t hsub(uint32_t a, uint32_t b) { uint32_t r; asm("sub.rn.f16x2 %0, %1, %2;\n" : "=r"(r) : "r"(a), "r"(b)); return r; }
__device__ __forceinline__ uint32_t hfma(uint32_t a, uint32_t b, uint32_t c) { uint32_t r; asm("fma.rn.f16x2 %0, %1, %2, %3;\n" : "=r"(r) : "r"(a), "r"(b), "r"(c)); return r; }
__device__ __forceinline__ uint32_t hfnma(uint32_t a, uint32_t b, uint32_t c) {
  uint32_t r;
  asm("{\n.reg .b32 t;\nneg.f16x2 t, %1;\nfma.rn.f16x2 %0, t, %2, %3;\n}\n" : "=r"(r) : "r"(a), "r"(b), "r"(c));
  return r;
}
__device__ __forceinline__ uint32_t hrefl(uint32_t p, uint32_t s) {
  uint32_t r;
  asm("{\n.reg .b32 t;\nneg.f16x2 t, %2;\nfma.rn.f16x2 %0, %1, %3, t;\n}\n" : "=r"(r) : "r"(p), "r"(s), "r"(0x40004000u));
  return r;
}
__device__ __forceinline__ void bfly(uint32_t xr, uint32_t xi, uint32_t tr, uint32_t ti, uint32_t yr, uint32_t yi, uint32_t ur,
                                     uint32_t ui, uint32_t& sr, uint32_t& si, uint32_t& dr, uint32_t& di) {
  const uint32_t pr = hfnma(xi, ti, hmul(xr, tr)), pi = hfma(xi, tr, hmul(xr, ti));
  sr = hfnma(yi, ui, hfma(yr, ur, pr));
  si = hfma(yi, ur, hfma(yr, ui, pi));
  dr = hrefl(pr, sr);
  di = hrefl(pi, si);
}
template <int BH> __device__ __forceinline__ void fft_e1(const uint32_t (&d)[32], const uint32_t (&tw)[16], uint32_t (&a2)[2][2][4]) {
#pragma unroll
  for (int be = 0; be < 2; be++)
#pragma unroll
    for (int s = 0; s < 2; s++) {
      const int o = 16 * s + 8 * be + 2 * BH, p = 2 * BH;
      bfly(d[o], d[o + 1], tw[p], tw[p + 1], d[o + 4], d[o + 5], tw[p + 4], tw[p + 5], a2[be][0][s], a2[be][0][2 + s],
           a2[be][1][s], a2[be][1][2 + s]);
    }
}
__device__ __forceinline__ uint32_t hfms(uint32_t a, uint32_t b, uint32_t c) {
  uint32_t r;
  asm("{\n.reg .b32 t;\nneg.f16x2 t, %3;\nfma.rn.f16x2 %0, %1, %2, t;\n}\n" : "=r"(r) : "r"(a), "r"(b), "r"(c));
  return r;
}
template <int C, int J> __device__ __forceinline__ void fft_e2(const uint32_t (&d0)[8], const uint32_t (&d1)[8], uint32_t (&a3)[2][4]) {
  const uint32_t ur = d0[2 * J], ui = d0[4 + 2 * J], hr = d0[2 * J + 1], hi = d0[5 + 2 * J];
  const uint32_t vr = d1[2 * J], vi = d1[4 + 2 * J], gr = d1[2 * J + 1], gi = d1[5 + 2 * J];
  const uint32_t pr = hfnma(ui, hi, hmul(ur, hr)), pi = hfma(ui, hr, hmul(ur, hi));
  a3[0][2 + C] = pr;
  a3[0][C] = pi;
  a3[1][2 + C] = hfnma(vi, hi, hfma(vr, hr, hfnma(ui, gi, hfms(ur, gr, pi))));
  a3[1][C] = hfma(vi, hr, hfma(vr, hi, hfma(ui, gr, hfma(ur, gi, pr))));
}
__device__ __forceinline__ void fft_e3(const uint32_t (&d)[2][8], const uint32_t (&tw)[16], uint32_t zaddr) {
#pragma unroll
  for (int rho = 0; rho < 2; rho++) {
    uint32_t zr[4], zi[4];
#pragma unroll
    for (int nb = 0; nb < 4; nb++) {
      const uint32_t xi = d[nb >> 1][2 * (nb & 1) + rho], xr = d[nb >> 1][4 + 2 * (nb & 1) + rho];
      const uint32_t tr = tw[8 + 4 * rho + 2 * (nb & 1)], ti = tw[9 + 4 * rho + 2 * (nb & 1)];
      zr[nb] = hfnma(xi, ti, hmul(xr, tr));
      zi[nb] = hfma(xi, tr, hmul(xr, ti));
    }
    stsm4(zaddr + rho * 1024, zr[0], zr[1], zr[2], zr[3]);
    stsm4(zaddr + rho * 1024 + 512, zi[0], zi[1], zi[2], zi[3]);
  }
}
__device__ __forceinline__ float bf_lo(uint32_t v) {
  uint32_t r;
  asm("prmt.b32 %0, %1, 0, 0x1044;\n" : "=r"(r) : "r"(v));
  return __uint_as_float(r);
}
__device__ __forceinline__ float bf_hi(uint32_t v) { return __uint_as_float(v & 0xffff0000u); }
__device__ __forceinline__ float ex2(float x) {
  float r;
  asm("ex2.approx.ftz.f32 %0, %1;\n" : "=f"(r) : "f"(x));
  return r;
}
__device__ __forceinline__ float rcp(float x) {
  float r;
  asm("rcp.approx.ftz.f32 %0, %1;\n" : "=f"(r) : "f"(x));
  return r;
}

__device__ __forceinline__ int g2_a(int s) { return ((0xA1054 >> (4 * s)) & 15) * 16384; }
__device__ __forceinline__ int g2_b(int s) { return ((0xCDB32 >> (4 * s)) & 15) * 16384; }
static_assert(OFF_U == 10 * 16384 && OFF_H == 12 * 16384 && OFF_OP == 4 * 16384, "units");
__device__ __forceinline__ int g2_k(int hp, int i) { return i < 2 ? hp ^ 1 ^ i : i < 4 ? (hp & ~1) ^ i : ((hp & ~3) + i) & 15; }
__device__ __forceinline__ int y_slot(int wg, int it) {
  static_assert(T_B2 == T_TW + 8192 && T_A1 == T_B2 + 4096, "y slots");
  return OFF_T + T_TW + ((it + 3) & 3) * 4096 + wg * 2048;
}

__device__ __forceinline__ void to_arr(uint32_t (&d)[4], uint4 v) { d[0] = v.x; d[1] = v.y; d[2] = v.z; d[3] = v.w; }

__device__ __forceinline__ void attn_stage(uint32_t sb, int blk, int lane, const float (&acc)[96], uint32_t (&k1)[2][4]) {
  const int lr = lane & 7, lm = lane >> 3;
  const uint32_t base = sb + OFF_VP + (blk * 16 + lr + 8 * (lm & 1)) * 128;
#pragma unroll
  for (int i = 0; i < 8; i++) k1[i >> 2][i & 3] = pack_bf16(acc[34 + 4 * i], acc[35 + 4 * i]);
  const uint32_t kh = sb + OFF_KH + blk * 2048 + lane * 16;
  sts128(kh, k1[0][0], k1[0][1], k1[0][2], k1[0][3]);
  sts128(kh + 512, k1[1][0], k1[1][1], k1[1][2], k1[1][3]);
#pragma unroll
  for (int j = 0; j < 8; j += 2)
    stsm4(base + (((j + (lm >> 1)) ^ lr) << 4), pack_bf16(acc[64 + 4 * j], acc[65 + 4 * j]),
          pack_bf16(acc[66 + 4 * j], acc[67 + 4 * j]), pack_bf16(acc[68 + 4 * j], acc[69 + 4 * j]),
          pack_bf16(acc[70 + 4 * j], acc[71 + 4 * j]));
}
__device__ __forceinline__ void attn_pack(const float (&acc)[96], uint32_t (&qa)[2][8], uint32_t (&k0)[2][4]) {
#pragma unroll
  for (int hd = 0; hd < 2; hd++) {
#pragma unroll
    for (int i = 0; i < 8; i++) {
      asm volatile("cvt.rn.bf16x2.f32 %0, %1, %2;\n" : "=r"(qa[hd][i]) : "f"(acc[16 * hd + 2 * i + 1]), "f"(acc[16 * hd + 2 * i]));
    }
#pragma unroll
    for (int i = 0; i < 4; i++) {
      asm volatile("cvt.rn.bf16x2.f32 %0, %1, %2;\n" : "=r"(k0[hd][i]) : "f"(acc[33 + 16 * hd + 4 * i]), "f"(acc[32 + 16 * hd + 4 * i]));
    }
  }
}
__device__ __forceinline__ void attn_own(const uint32_t (&k0)[2][4], const uint32_t (&k1)[2][4], bool le0, bool le1,
                                         const uint32_t (&qa)[2][8], float (&l)[2][4]) {
#pragma unroll
  for (int hd = 0; hd < 2; hd++) {
    float s0[4], s1[4];
    mma16816_z(s0, qa[hd][0], qa[hd][1], qa[hd][2], qa[hd][3], k0[hd][0], k0[hd][1]);
    mma16816_z(s1, qa[hd][0], qa[hd][1], qa[hd][2], qa[hd][3], k1[hd][0], k1[hd][1]);
    mma16816(s0, qa[hd][4], qa[hd][5], qa[hd][6], qa[hd][7], k0[hd][2], k0[hd][3]);
    mma16816(s1, qa[hd][4], qa[hd][5], qa[hd][6], qa[hd][7], k1[hd][2], k1[hd][3]);
    l[hd][0] = s0[0];
    l[hd][1] = s0[1];
    l[hd][2] = le0 ? s1[2] : s0[2];
    l[hd][3] = le1 ? s1[3] : s0[3];
  }
}
template <int N> __device__ __forceinline__ void quad_softmax(float (&x)[N][2], uint32_t (&pp)[N]) {
  const float c2 = 1.4426950408889634f;
  uint32_t q[N], mx[N / 2];
#pragma unroll
  for (int n = 0; n < N; n++) {
    const uint32_t r = pack_bf16(x[n][0], x[n][1]);
    q[n] = bfma2(r, 0x3e353e35u, bmul2(r, 0x379e379eu));
    x[n][0] = bf_lo(q[n]);
    x[n][1] = bf_hi(q[n]);
  }
#pragma unroll
  for (int n = 0; n < N / 2; n++)
    mx[n] = bmax2(__byte_perm(q[2 * n], q[2 * n + 1], 0x5410), __byte_perm(q[2 * n], q[2 * n + 1], 0x7632));
#pragma unroll
  for (int o = 1; o <= 2; o++)
#pragma unroll
    for (int n = 0; n < N / 2; n++) mx[n] = bmax2(mx[n], __shfl_xor_sync(0xffffffffu, mx[n], o));
  float m[N], t[N];
#pragma unroll
  for (int n = 0; n < N / 2; n++) {
    m[2 * n] = bf_lo(mx[n]);
    m[2 * n + 1] = bf_hi(mx[n]);
  }
#pragma unroll
  for (int n = 0; n < N; n++) {
    const float nm = -m[n] * c2;
    x[n][0] = ex2(fmaf(x[n][0], c2, nm));
    x[n][1] = ex2(fmaf(x[n][1], c2, nm));
    t[n] = x[n][0] + x[n][1];
  }
#pragma unroll
  for (int o = 1; o <= 2; o++)
#pragma unroll
    for (int n = 0; n < N; n++) t[n] += __shfl_xor_sync(0xffffffffu, t[n], o);
#pragma unroll
  for (int n = 0; n < N; n++) {
    const float inv = rcp(t[n]);
    pp[n] = pack_bf16(x[n][0] * inv, x[n][1] * inv);
  }
}
__device__ __forceinline__ void attn_pv(uint32_t dst, const uint32_t (&va)[4], const uint32_t (&vb)[4], uint32_t pp,
                                        uint32_t maskLE) {
  const uint32_t b0 = pp & ~maskLE, b1 = pp & maskLE;
  float oa[4], ob[4];
  mma16816_z(oa, va[0], va[1], va[2], va[3], b0, b1);
  mma16816_z(ob, vb[0], vb[1], vb[2], vb[3], b0, b1);
  stsm4t(dst, pack_bf16(oa[0], oa[1]), pack_bf16(oa[2], oa[3]), pack_bf16(ob[0], ob[1]), pack_bf16(ob[2], ob[3]));
}

template <int MODE>
__global__ void __cluster_dims__(2, 1, 1) __launch_bounds__(NTHREADS, 1)
fused_kernel(const Params p, const __grid_constant__ CUtensorMap tmX, const __grid_constant__ CUtensorMap tmW,
             const __grid_constant__ CUtensorMap tmWo,
             const __grid_constant__ CUtensorMap tmQ,
             const __grid_constant__ CUtensorMap tmXh, const __grid_constant__ CUtensorMap tmWh) {
  extern __shared__ __align__(1024) uint8_t smem[];
  const uint32_t sb = smem_u32(smem);
  const uint32_t bars = sb + OFF_BAR;
  const int tid = threadIdx.x, lane = tid & 31, warp = __shfl_sync(0xffffffffu, tid >> 5, 0);
  const int rank = blockIdx.x & 1;
  const bool halo_cta = blockIdx.x < 4;
  if (halo_cta && MODE != 0) return;
  int grp, mem;
  {
    const int t = (blockIdx.x >> 1) - 4, u = t - 32;
    const int q7 = (u * 37) >> 8;
    const bool lo = (unsigned)t < 32u, mid = (unsigned)u < 28u;
    grp = lo ? (t & 7) : (mid ? 1 + u - 7 * q7 : 0);
    mem = lo ? (t >> 3) : (mid ? 4 + q7 : (t < 0 ? t + 6 : t - 54));
  }
  const int rg = (grp >> 2) * 4 + (mem >> 1), hp = (grp & 3) * 4 + (mem & 1) * 2 + rank;
  const int rb2 = (grp >> 2) * 8 + mem, cb2 = (grp & 3) * 2 + rank;
  const int chb = grp * 16 + mem * 2 + rank;
  const int cta = rg * 16 + hp;
  const int par = rg >> 2, gidx = rg & 3;

  if (tid < 256 && !halo_cta && MODE != 2) {
    const int r = tid >> 3, c = tid & 7;
    const uint32_t so = r * 128 + ((c ^ (r & 7)) << 4);
    const __nv_bfloat16* wg0 = p.w + (size_t)r * (3 * DM) + hp * 64 + c * 8;
    const __nv_bfloat16* xg0 = p.x + (size_t)(2 * (gidx * 256 + r) + par) * DM + c * 8;
#pragma unroll
    for (int j = 0; j < 3; j++) cp_async16n(sb + OFF_1B + j * 4096 + so, wg0 + j * DM);
#pragma unroll
    for (int i = 0; i < 8; i++) cp_async16n(sb + i * 4096 + so, xg0 + (size_t)i * 64 * DM);
    asm volatile("cp.async.commit_group;\n" ::: "memory");
  }
  if (tid == 256) {
    prefetch_tmap(halo_cta ? &tmXh : &tmX);
#pragma unroll
    for (int i = 0; i < NS1B; i++) mbar_init(bars + 8 * (BAR_FULLB + i), 1);
#pragma unroll
    for (int i = 0; i < NS1A; i++) mbar_init(bars + 8 * (BAR_FULLA + i), 1);
    asm volatile("fence.mbarrier_init.release.cluster;\n" ::: "memory");
    if (!halo_cta && MODE != 2) {
      mbar_expect_tx(bars + 8 * (BAR_FULLB + 1), STG1B);
      tma_load_3d(sb + OFF_1B + 1 * STG1B, &tmW, bars + 8 * (BAR_FULLB + 1), hp * 64, 32, 0);
      mbar_expect_tx(bars + 8 * (BAR_FULLB + 2), STG1B);
      tma_load_3d(sb + OFF_1B + 2 * STG1B, &tmW, bars + 8 * (BAR_FULLB + 2), hp * 64, 64, 0);
    } else {
      prefetch_tmap(&tmWh);
    }
  } else if (tid == 288) {
#pragma unroll
    for (int i = 0; i < NS1A; i++) mbar_init(bars + 8 * (BAR_EMPTYA + i), 4);
#pragma unroll
    for (int i = 0; i < NS1B; i++) mbar_init(bars + 8 * (BAR_EMPTYB + i), 2);
    asm volatile("fence.mbarrier_init.release.cluster;\n" ::: "memory");
  } else if (tid == 320) {
#pragma unroll
    for (int i = 0; i < NS2; i++) {
      mbar_init(bars + 8 * (BAR_FULL2 + i), 1);
      mbar_init(bars + 8 * (BAR_EMPTY2 + i), 4);
    }
    mbar_init(bars + 8 * BAR_DEAD, 2);
    mbar_init(bars + 8 * (BAR_DEAD + 1), 2);
    mbar_init(bars + 8 * BAR_X, 2);
    mbar_init(bars + 8 * BAR_REL, 2);
    asm volatile("fence.mbarrier_init.release.cluster;\n" ::: "memory");
  } else if (tid == 352) {
    mbar_init(bars + 8 * BAR_T, 1);
    mbar_init(bars + 8 * BAR_UH, 3);
    mbar_init(bars + 8 * BAR_LFREE, 4);
    mbar_init(bars + 8 * BAR_LAND, 1);
    mbar_init(bars + 8 * BAR_U, 1);
    mbar_init(bars + 8 * BAR_Q, 1);
    mbar_init(bars + 8 * BAR_STG, 9);
    asm volatile("fence.mbarrier_init.release.cluster;\n" ::: "memory");
  }
  if (warp == 8) PROF2(23);
  cluster_sync_all();
  if (warp == 8) PROF2(24);

  if (warp >= 8) {
    const int hw = warp - 8;
    const int lr = lane & 7, lm = lane >> 3;
    auto g1_issue_a = [&](int j, int s) {
      const uint32_t fb = bars + 8 * (BAR_FULLA + s);
      mbar_expect_tx(fb, STG1A);
      tma_load_3d_mc(sb + s * STG1A + rank * 16384, &tmX, fb, j * 64, par, gidx * 256 + rank * 128);
    };
    auto g1_issue_b = [&](int kb, int s) {
      const uint32_t fb = bars + 8 * (BAR_FULLB + s);
      mbar_expect_tx(fb, STG1B);
      tma_load_3d(sb + OFF_1B + s * STG1B, &tmW, fb, hp * 64, kb * 32, 0);
    };
    asm volatile("setmaxnreg.dec.sync.aligned.u32 %0;\n" :: "n"(REG_HELP));

    if (halo_cta) {
      if (hw == 0) {
        int s = 0, ph = 1;
#pragma unroll 1
        for (int kb = 0; kb < 16; kb++) {
          mbar_wait(bars + 8 * (BAR_EMPTYB + s), ph);
          const uint32_t fb = bars + 8 * (BAR_FULLB + s), st = sb + s * STGH;
          if (elect_one()) {
            mbar_expect_tx(fb, STGH);
            tma_load_4d(st, &tmXh, fb, kb * 64, 248, 0, 0);
            tma_load_3d(st + 8192, &tmWh, fb, 0, kb * 64, 16 + blockIdx.x * 4);
            tma_load_3d(st + 8192 + 32768, &tmWh, fb, 0, kb * 64, 32 + blockIdx.x * 4);
          }
          if (++s == 3) { s = 0; ph ^= 1; }
        }
      }
      __syncwarp();
    } else if (hw == 0) {
      uint32_t epoch = 0;
      if (lane < (MODE == 2 ? NS2 : 2)) mbar_arrive_cluster_n(mapa(bars, rank) + 8 * (BAR_EMPTY2 + lane), 4);
      if (MODE != 2) {
      epoch = ld_relaxed(g_flag_o + 2 * cta) + 1;
      if (lane == 0) {
        mbar_expect_tx(bars + 8 * BAR_U, 32768);
        mbar_expect_tx(bars + 8 * BAR_LAND, 32768);
        mbar_expect_tx(bars + 8 * BAR_Q, 32768);
        mbar_expect_tx(bars + 8 * BAR_T, T_END);
      }
      {
        int sa = 1, pha = 1, sbb = 2, phb = 1;
#pragma unroll 1
        for (int kb = 2; kb < 32; kb++) {
          if (!(kb & 1)) {
            mbar_wait(bars + 8 * (BAR_EMPTYA + sa), pha);
            if (elect_one()) g1_issue_a(kb >> 1, sa);
            if (++sa == NS1A) { sa = 0; pha ^= 1; }
          }
          mbar_wait(bars + 8 * (BAR_EMPTYB + sbb), phb);
          if (kb > 2 && elect_one()) g1_issue_b(kb, sbb);
          __syncwarp();
          if (kb >= PF0 && kb < PF0 + 12)
            prefetch_l2((kb < PF0 + 8 ? p.q + (size_t)chb * 16384 + (kb - PF0) * 2048 : p.wo + (size_t)chb * 8192 + (kb - PF0 - 8) * 2048) + lane * 64);
          if (kb == 4) PROF2(27);
          if (kb == 1) PROF2(38);
          if (kb == 2) PROF2(39);
          if (++sbb == NS1B) { sbb = 0; phb ^= 1; }
        }
      }
      static_assert(32 % NS1B == 2 && (32 / NS1B) % 2 == 0 && OFF_Q == OFF_1B && 2 * STG1B == 6 * 4096, "slots / parity of these loads");
      const uint8_t* tab = reinterpret_cast<const uint8_t*>(g_tab);
      if (lane == 0) {
        prefetch_tmap(&tmWo);
        prefetch_tmap(&tmQ);
        bulk_load(sb + OFF_T + T_A1, tab + T_A1, T_END - T_A1, bars + 8 * BAR_T);
        mbar_wait(bars + 8 * (BAR_EMPTYB + 2), 1);
        tma_load_5d(sb + OFF_Q + 6 * 4096, &tmQ, bars + 8 * BAR_Q, (chb & ~1) * 8, rank * 32 + 24);
        tma_load_5d(sb + OFF_Q + 7 * 4096, &tmQ, bars + 8 * BAR_Q, (chb & ~1) * 8, rank * 32 + 28);
        if (gidx != 0) wait_flag(g_flag_h + (hp >> 2), epoch);
      }
      __syncwarp();
      {
        uint4 hk0 = make_uint4(0, 0, 0, 0), hk1 = hk0, hv0 = hk0, hv1 = hk0;
        if (gidx != 0) {
          const uint4* src = g_halo + cta * 128 + lane;
          hk0 = __ldcg(src); hk1 = __ldcg(src + 32); hv0 = __ldcg(src + 64); hv1 = __ldcg(src + 96);
        }
        if (lane == 0) {
          mbar_wait(bars + 8 * (BAR_EMPTYB + 3), 1);
          bulk_load(sb + OFF_T, tab, T_TW, bars + 8 * BAR_T);
        }
        __syncwarp();
        PROF2(18);
        sts128(sb + OFF_L0 + 1024 + lane * 16, hk0.x, hk0.y, hk0.z, hk0.w);
        sts128(sb + OFF_L0 + 1536 + lane * 16, hk1.x, hk1.y, hk1.z, hk1.w);
        stsm4(sb + OFF_L0 + lr * 128 + ((lm ^ lr) << 4), hv0.x, hv0.y, hv0.z, hv0.w);
        stsm4(sb + OFF_L0 + lr * 128 + (((4 + lm) ^ lr) << 4), hv1.x, hv1.y, hv1.z, hv1.w);
        __syncwarp();
        if (lane == 0) {
          mbar_arrive(bars + 8 * BAR_STG);
          mbar_wait(bars + 8 * (BAR_EMPTYB + 4), 1);
          bulk_load(sb + OFF_T + T_TW, tab + T_TW, T_A1 - T_TW, bars + 8 * BAR_T);
          mbar_wait(bars + 8 * BAR_EMPTYB, 0);
#pragma unroll 1
          for (int i = 0; i < 6; i++) tma_load_5d(sb + OFF_Q + i * 4096, &tmQ, bars + 8 * BAR_Q, (chb & ~1) * 8, rank * 32 + i * 4);
        }
        __syncwarp();
      }
      }
      if (MODE != 1) {
        auto korder = [&](int i) { return MODE == 2 ? i : g2_k(hp, i); };
        if (MODE == 0) {
          mbar_wait_idle(bars + 8 * (BAR_EMPTY2 + 2), 0);
          if (elect_one()) {
            mbar_expect_tx(bars + 8 * BAR_FULL2, STG2);
            tma_load_3d(sb + g2_b(0), &tmWo, bars + 8 * BAR_FULL2, 0, korder(0) * 64, cb2 * 2);
            tma_load_3d(sb + g2_b(1), &tmWo, bars + 8 * (BAR_FULL2 + 1), 0, korder(1) * 64, cb2 * 2);
          }
        }
        PROF2(20);
        const __nv_bfloat16* osrc = g_o + (size_t)(rb2 >> 1) * 16 * 16384 + ((rb2 & 1) * 2 + rank) * 4096;
        const uint32_t* flag = g_flag_o + (rb2 >> 1) * 32 + korder(lane & 15) * 2 + (rb2 & 1);
        uint32_t ready = MODE == 0 ? 0u : ~0u;
#pragma unroll
        for (int i = MODE == 0 ? 2 : 0; i < 16; i++) {
          const int kb = korder(i), s = i % NS2, ph = (i / NS2) & 1;
          const uint32_t fb = bars + 8 * (BAR_FULL2 + s);
          if (!((ready >> i) & 1)) {
            int n = 0;
            do {
              ready |= __ballot_sync(0xffffffffu, ld_acquire(flag) == epoch);
            } while (!((ready >> i) & 1) && ++n < SPIN_LIMIT);
            fence_async_all();
          }
          if (i == 2) PROF(21);
          mbar_wait(bars + 8 * (BAR_EMPTY2 + s), ph);
          if (elect_one()) {
            mbar_expect_tx(fb, STG2);
            asm volatile(
                "cp.async.bulk.shared::cluster.global.mbarrier::complete_tx::bytes.multicast::cluster [%0], [%1], %2, [%3], %4;\n"
                ::"r"(sb + g2_a(s) + rank * 8192), "l"(osrc + kb * 16384), "r"(8192), "r"(fb), "h"((uint16_t)3) : "memory");
            if (MODE != 0 || i >= 4) tma_load_3d(sb + g2_b(s), &tmWo, fb, 0, kb * 64, cb2 * 2);
          }
          if (i == 3) PROF(37);

        }
      }
      __syncwarp();
    } else if (MODE != 2) {
      {
        const int g = lane >> 2, t = lane & 3;
        uint32_t w[2][4];
#pragma unroll
        for (int h = 0; h < 2; h++) {
          const uint2 x = __ldg(reinterpret_cast<const uint2*>(p.shift_k + ((chb & ~1) * 8 + h * 8 + g) * 4));
          w[h][0] = __byte_perm(x.x, x.x, 0x1010);
          w[h][1] = __byte_perm(x.x, x.x, 0x3232);
          w[h][2] = __byte_perm(x.y, x.y, 0x1010);
          w[h][3] = __byte_perm(x.y, x.y, 0x3232);
        }
        auto swz = [](int r) { return (((r & 29) | ((r ^ (r >> 2)) & 2)) << 5) | (r & 16); };
        const uint32_t kring = sb + OFF_H + (hw - 1) * 8192, vring = kring + 4096;
        const int s0 = rank * 32 + (hw - 1) * 11, s1 = hw == 3 ? rank * 32 + 32 : s0 + 11;
        const size_t goff = (size_t)(lane >> 1) * DM + (chb & ~1) * 8 + (lane & 1) * 8;
        const __nv_bfloat16* kg = p.k + goff;
        const __nv_bfloat16* vg = p.v + goff;
        const uint32_t d0 = swz(lane >> 1) ^ ((lane & 1) << 4), d1 = swz(16 + (lane >> 1)) ^ ((lane & 1) << 4);
        auto issue = [&](int st) {
          const uint32_t so = (st & 3) << 10;
          cp_async16(kring + so + d0, kg + (size_t)st * 32 * DM, 16);
          cp_async16(kring + so + d1, kg + (size_t)(st * 32 + 16) * DM, 16);
          cp_async16(vring + so + d0, vg + (size_t)st * 32 * DM, 16);
          cp_async16(vring + so + d1, vg + (size_t)(st * 32 + 16) * DM, 16);
        };
        const int xa = 8 * (lr >> 1) + 2 * lm + (lr & 1), xb = 8 * (lr >> 1) - 4 + 2 * (lm & 1) + (lr & 1);
        const uint32_t la = swz(xa), lb = swz(xb & 31);
        const int backb = xb < 0 ? 1 : 0;
        const uint32_t ud[2] = {mapa(sb + OFF_U + g * 4096 + t * 16, 0), mapa(sb + OFF_U + g * 4096 + t * 16, 1)};
        const uint32_t ub[2] = {mapa(bars + 8 * BAR_U, 0), mapa(bars + 8 * BAR_U, 1)};
        if (lane == 0) mbar_wait(bars + 8 * (BAR_FULLB + NS1B - 1), 0);
        __syncwarp();
        if (lane >= 24) cp_async16(kring + (((s0 - 1) & 3) << 10) + d1, s0 > 0 ? kg + (size_t)(s0 * 32 - 16) * DM : kg, s0 > 0 ? 16 : 0);
        issue(s0);
        asm volatile("cp.async.commit_group;\n" ::: "memory");
        issue(s0 + 1);
        asm volatile("cp.async.commit_group;\n" ::: "memory");
#pragma unroll 1
        for (int st = s0; st < s1; st++) {
          if (st + 2 < s1) issue(st + 2);
          if (hw == 1 && st - s0 < 8) prefetch_l2(p.ssm_k + (size_t)(chb * 8 + st - s0) * SEQ + lane * 64);
          if (hw == 2 && st == s0 + 4 && lane < 2) prefetch_l2(g_tab + (chb * 2 + lane) * 32);
          const uint32_t uo = (st ^ ((g ^ (st >> 2)) & 1)) * 64;
          asm volatile("cp.async.commit_group;\n" ::: "memory");
          asm volatile("cp.async.wait_group 2;\n" ::: "memory");
          __syncwarp();
#pragma unroll
          for (int h = 0; h < 2; h++) {
            uint32_t e[6], vv[4], e4[4];
            ldsm4t(e4, kring + ((st & 3) << 10) + (la ^ (h << 4)));
            ldsm2t(e[0], e[1], kring + (((st - backb) & 3) << 10) + (lb ^ (h << 4)));
            ldsm4t(vv, vring + ((st & 3) << 10) + (la ^ (h << 4)));
            e[2] = e4[0]; e[3] = e4[1]; e[4] = e4[2]; e[5] = e4[3];
            uint32_t o[5];
#pragma unroll
            for (int i = 0; i < 5; i++) o[i] = __byte_perm(e[i], e[i + 1], 0x5432);
#pragma unroll
            for (int i = 0; i < 4; i++) {
              uint32_t a = bmul2(o[i], w[h][3]);
              a = bfma2(e[i + 1], w[h][2], a);
              a = bfma2(o[i + 1], w[h][1], a);
              a = bfma2(e[i + 2], w[h][0], a);
              vv[i] = bmul2(a, vv[i]);
            }
            st_async128(ud[h] + uo, ub[h], vv[0], vv[1], vv[2], vv[3]);
          }
          __syncwarp();
        }
        PROF(16);
      }
      {
        const int rw = (lane >> 3) + (lane & 4), ck = lane & 3;
        const uint32_t so = rw * 64 + ck * 16, dof = rw * 128 + ((ck ^ rw) << 4);
        const uint8_t* hsrc = reinterpret_cast<const uint8_t*>(p.ssm_k + (size_t)chb * 8 * SEQ) + so;
        const float dv = lane < 8 ? __bfloat162float(p.ssm_D[chb * 8 + lane]) : 0.f;
        uint32_t x[32];
        auto load = [&](const uint8_t* src, int i) {
          asm volatile("ld.v4.u32 {%0,%1,%2,%3}, [%4];\n" : "=r"(x[4 * i]), "=r"(x[4 * i + 1]), "=r"(x[4 * i + 2]), "=r"(x[4 * i + 3])
                       : "l"(src + i * 512) : "memory");
        };
#pragma unroll
        for (int i = 0; i < 8; i++) load(hsrc + (hw - 1) * 4096, i);
        nb_sync(NB_HELP3, 96);
        mbar_wait(bars + 8 * BAR_U, 0);
        int eh = 0;
#pragma unroll 1
        for (int n = 2 * (hw - 1); n < 16; n += (n & 1) ? 5 : 1) {
          const int c = n >> 1;
          const uint8_t* nsrc = (n & 1) ? hsrc + (c < 5 ? c + 3 : c) * 4096
                                        : smem + OFF_U + c * 4096 + (so ^ (((c ^ (lane >> 2)) & 1) << 6));
          const uint32_t dst = sb + ((n & 1) ? OFF_U : OFF_H) + c * 4096 + dof;
          const float dc = __shfl_sync(0xffffffffu, dv, c);
          const float h0 = bf_lo(x[0]) + ((lane | (n & 1)) == 0 ? dc : 0.f), h1 = bf_hi(x[0]);
          x[0] = pack_bf16(h0, h1);
          uint32_t m[2] = {x[0], x[1]};
#pragma unroll
          for (int i = 2; i < 32; i++) asm("max.xorsign.abs.bf16x2 %0, %0, %1;\n" : "+r"(m[i & 1]) : "r"(x[i]));
          asm("max.xorsign.abs.bf16x2 %0, %0, %1;\n" : "+r"(m[0]) : "r"(m[1]));
          const uint32_t e = max(__reduce_max_sync(0xffffffffu, max((m[0] >> 7) & 255u, (m[0] >> 23) & 255u)), 5u);
          const uint32_t sc = (259u - e) * 0x00800080u;
#pragma unroll
          for (int i = 0; i < 8; i++) {
            uint32_t o[4];
#pragma unroll
            for (int j = 0; j < 4; j++) {
              const uint32_t v = bmul2(x[4 * i + j], sc);
              asm("cvt.rn.f16x2.f32 %0, %1, %2;\n" : "=r"(o[j]) : "f"(bf_hi(v)), "f"(i + j == 0 ? h0 * bf_hi(sc) : bf_lo(v)));
            }
            sts128((dst + (i & 3) * 1024) ^ ((i >> 2) << 6), o[0], o[1], o[2], o[3]);
            load(nsrc, i);
          }
          if (n & 1) {
            const int f = min(max((int)e + eh - 129, 0), 254);
            if (lane == 0) asm volatile("st.shared.u32 [%0], %1;\n" ::"r"(sb + OFF_SC + c * 4), "r"(f << 23) : "memory");
          }
          eh = e;
        }
        fence_async_smem();
        __syncwarp();
        if (lane == 0) mbar_arrive(bars + 8 * BAR_UH);
        PROF(32);
      }
      if (hw < 3) {
        const uint32_t rb = mapa(bars, lane & 1);
        const uint32_t epoch = ld_relaxed(g_flag_o + 2 * cta + hw - 1) + 1;
        const bool own = hw - 1 == (rb2 & 1);
        nb_sync(NB_OREADY + hw - 1, 160);
        if (lane == 0) {
          asm volatile("cp.async.bulk.global.shared::cta.bulk_group [%0], [%1], %2;\n" ::"l"(g_o + (size_t)cta * 16384 + (hw - 1) * 8192),
                       "r"(sb + OFF_OP + (own ? 16384 : 0)), "r"(16384) : "memory");
          bulk_commit();
        }
        if (lane < 2) {
          mbar_arrive_cluster(rb + 8 * (BAR_EMPTY2 + 2));
          mbar_arrive_cluster(rb + 8 * (BAR_EMPTY2 + 3));
        }
        if (lane == 0) {
          bulk_wait0();
          if (own) mbar_expect_tx(bars + 8 * (BAR_FULL2 + 1), 16384);
          mbar_arrive_cluster(mapa(bars, own ? rank : rank ^ 1) + 8 * BAR_X);
          st_release(g_flag_o + 2 * cta + hw - 1, epoch);
          mbar_arrive(bars + 8 * BAR_REL);
        }
        __syncwarp();
        PROF(17);
      } else {
        mbar_wait_idle(bars + 8 * BAR_REL, 0);
        if (MODE == 0) {
          mbar_wait(bars + 8 * BAR_X, 0);
          if (elect_one())
            asm volatile("cp.async.bulk.shared::cluster.shared::cta.mbarrier::complete_tx::bytes [%0], [%1], %2, [%3];\n"
                         ::"r"(mapa(sb + OFF_OP, rank ^ 1)), "r"(sb + OFF_OP + 16384), "r"(16384),
                         "r"(mapa(bars + 8 * BAR_FULL2, rank ^ 1)) : "memory");
        }
        if (MODE == 0) {
          mbar_wait_idle(bars + 8 * BAR_DEAD, 0);
          if (elect_one()) {
            tma_load_3d(sb + g2_b(2), &tmWo, bars + 8 * (BAR_FULL2 + 2), 0, g2_k(hp, 2) * 64, cb2 * 2);
            tma_load_3d(sb + g2_b(3), &tmWo, bars + 8 * (BAR_FULL2 + 3), 0, g2_k(hp, 3) * 64, cb2 * 2);
          }
        }
        __syncwarp();
      }
      {
        const int c8 = (4 * (lr >> 1) + 2 * (lm & 1) + (lr & 1)) & 7;
        const bool own = (lr >> 2) == rank;
        const uint32_t ya = sb + (own ? y_slot(c8 & 1, c8 >> 1) : OFF_LAND + c8 * 2048);
        const uint32_t yx = ((lm >> 1) ^ lr) << 4;
        const int row = (lane >> 3) * 8 + ((lane >> 2) & 1);
        uint2* og = reinterpret_cast<uint2*>(p.out + (size_t)(rank * 1024 + row) * (2 * DM) + (chb & ~1) * 8 + (lane & 3) * 4);
        const uint32_t qa = sb + OFF_Q + lane * 8;
        mbar_wait(bars + 8 * BAR_Q, 0);
        mbar_wait_idle(bars + 8 * BAR_LAND, 0);
        PROF(33);
        const uint32_t t0 = clock();
#pragma unroll 1
        for (int j = hw - 1; j < 16; j += 3) {
          uint32_t y[4][4];
          uint2 q[8];
          while ((uint32_t)clock() - t0 < j * PACE) __nanosleep(40);
          const uint32_t qj = qa + j * 2048;
#pragma unroll
          for (int i = 0; i < 4; i++) ldsm4t(y[i], ya + j * 128 + (yx ^ (i << 5)));
#pragma unroll
          for (int i = 0; i < 8; i++) q[i] = lds64(qj + i * 256);
#pragma unroll
          for (int i = 0; i < 8; i++)
            og[(size_t)(j * 64 + (i >> 2) * 32 + (i & 3) * 2) * (2 * DM / 4)] =
                make_uint2(bmul2(q[i].x, y[i >> 1][2 * (i & 1)]), bmul2(q[i].y, y[i >> 1][2 * (i & 1) + 1]));
        }
      }
      PROF(22);
    }
    cluster_sync_all();
  } else {
    asm volatile("setmaxnreg.inc.sync.aligned.u32 %0;\n" :: "n"(REG_MATH));
    if (warp == 0) PROF2(26);
    const int wg = warp >> 2;
    const int wtid = tid & 127;
    const bool signaller = (wtid == 0) || (wtid == 32);
    const uint32_t rbars = mapa(bars, wtid >> 5 & 1);

    if (halo_cta) {
      const uint32_t epoch = ld_relaxed(g_flag_h + blockIdx.x) + 1;
      float acc0[64], acc1[64];
      int s = 0, ph = 0;
#pragma unroll 1
      for (int kb = 0; kb < 16; kb++) {
        mbar_wait(bars + 8 * (BAR_FULLB + s), ph);
        const uint32_t st = sb + s * STGH;
        const uint64_t da = mkdesc(st, 16, 1024, 1);
        const uint64_t db = mkdesc(st + 8192 + wg * 32768, 8192, 1024, 1);
        wg_fence();
#pragma unroll
        for (int kk = 0; kk < 4; kk++) {
          wgmma_n128(acc0, da + 2 * kk, db + 128 * kk, kb + kk);
          wgmma_n128(acc1, da + 2 * kk, db + 1024 + 128 * kk, kb + kk);
        }
        wg_commit();
        wg_wait<0>();
        if (wtid == 0) mbar_arrive(bars + 8 * (BAR_EMPTYB + s));
        if (++s == 3) { s = 0; ph ^= 1; }
      }
      fence_regs(acc0);
      fence_regs(acc1);
      if ((warp & 3) != 3) {
#pragma unroll
        for (int hh = 0; hh < 2; hh++) {
          uint4* dst = g_halo + ((hh * 4 + (warp & 3) + 1) * 16 + blockIdx.x * 4) * 128 + wg * 64 + lane;
#pragma unroll
          for (int j = 0; j < 4; j++) {
            const int o = 16 * j + 2 * hh;
            dst[(j >> 1) * 128 + (j & 1) * 32] =
                make_uint4(pack_bf16(acc0[o], acc0[o + 1]), pack_bf16(acc0[o + 4], acc0[o + 5]),
                           pack_bf16(acc0[o + 8], acc0[o + 9]), pack_bf16(acc0[o + 12], acc0[o + 13]));
            dst[(2 + (j >> 1)) * 128 + (j & 1) * 32] =
                make_uint4(pack_bf16(acc1[o], acc1[o + 1]), pack_bf16(acc1[o + 4], acc1[o + 5]),
                           pack_bf16(acc1[o + 8], acc1[o + 9]), pack_bf16(acc1[o + 12], acc1[o + 13]));
          }
        }
      }
      nb_sync(NB_G1DONE, 256);
      if (tid == 0) st_release(g_flag_h + blockIdx.x, epoch);
      PROF(36);
      cluster_sync_all();
      return;
    }

    float acc[64];
    auto g2_step = [&](int s, int kb) {
      const uint64_t da = mkdesc(sb + g2_a(s) + wg * 8192, 16, 1024, 1);
      const uint64_t db = mkdesc(sb + g2_b(s), 8192, 1024, 1);
      wg_fence();
      wgmma_n128(acc, da, db, kb);
      wgmma_n128(acc, da + 2, db + 128, 1);
      wgmma_n128(acc, da + 4, db + 256, 1);
      wgmma_n128(acc, da + 6, db + 384, 1);
      wg_commit();
    };

    if (MODE != 2) {
    uint32_t a1[2][4], tw[16], d1[32];
    const uint32_t tb = sb + OFF_T + wtid * 16;
    const uint64_t dx = mkdesc(sb + OFF_U + wg * 4096, OFF_H - OFF_U, 1024, 1);
    auto s1 = [&](int it) {
      hmma_n128t<0>(d1, a1[0], dx + it * 512);
      hmma_n128t<1>(d1, a1[1], dx + it * 512 + 128);
      wg_commit();
    };
    auto ldtw = [&](int i) {
      const uint4 v = lds128(tb + T_TW + i * 2048);
      tw[4 * i] = v.x; tw[4 * i + 1] = v.y; tw[4 * i + 2] = v.z; tw[4 * i + 3] = v.w;
    };
    {
      float acc0[96], acc1[96];
      int sa = 0, pha = 0, sbb = 0, phb = 0;
      asm volatile("cp.async.wait_group 0;\n" ::: "memory");
      fence_async_smem();
      nb_sync(NB_FIRST, 256);
      if (tid == 0) {
        mbar_arrive(bars + 8 * BAR_FULLA);
        mbar_arrive(bars + 8 * BAR_FULLB);
      }
      PROF(0 + wg);
#pragma unroll 1
      for (int kb = 0; kb < 30; kb++) {
        if (!(kb & 1)) mbar_wait(bars + 8 * (BAR_FULLA + sa), pha);
        mbar_wait(bars + 8 * (BAR_FULLB + sbb), phb);
        if (kb == 0) PROF2(0 + wg);
        if (kb == 4 && wg == 0) PROF2(28);
        if (kb == 8 && wg == 0) PROF2(29);
        if (kb == 16 && wg == 0) PROF2(30);
        const uint64_t da = mkdesc(sb + sa * STG1A + wg * 16384 + (kb & 1) * 64, 16, 1024, 1);
        const uint64_t db = mkdesc(sb + OFF_1B + sbb * STG1B, 4096, 1024, 1);
        wg_fence();
        wgmma_n192(acc0, da, db, kb);
        wgmma_n192(acc1, da + 512, db, kb);
        wgmma_n192(acc0, da + 2, db + 128, 1);
        wgmma_n192(acc1, da + 514, db + 128, 1);
        wg_commit();
        wg_wait<1>();
        if (kb > 0) {
          if (wtid == 64) mbar_arrive(bars + 8 * (BAR_EMPTYB + (sbb == 0 ? NS1B - 1 : sbb - 1)));
          if (!(kb & 1) && signaller) mbar_arrive_cluster(rbars + 8 * (BAR_EMPTYA + (sa == 0 ? NS1A - 1 : sa - 1)));
        }
        if (++sbb == NS1B) { sbb = 0; phb ^= 1; }
        if ((kb & 1) && ++sa == NS1A) { sa = 0; pha ^= 1; }
      }
      const int blk0 = wg * 8 + (warp & 3);
      const int lr = lane & 7, lm = lane >> 3;
      const bool le0 = 2 * (lane & 3) <= (lane >> 2), le1 = 2 * (lane & 3) + 1 <= (lane >> 2);
      const uint32_t maskLE = (le0 ? 0x0000FFFFu : 0u) | (le1 ? 0xFFFF0000u : 0u);
      uint32_t k0[2][2][4], k1[2][2][4], qa[2][2][8];
      float l[2][2][4];
      {
        static_assert(15 % NS1A == 0 && 30 % NS1B == 0, "slots of the last k blocks");
        mbar_wait(bars + 8 * BAR_FULLA, 1);
        mbar_wait(bars + 8 * BAR_FULLB, 0);
        mbar_wait(bars + 8 * (BAR_FULLB + 1), 0);
        const uint64_t da = mkdesc(sb + wg * 16384, 16, 1024, 1);
        const uint64_t db = mkdesc(sb + OFF_1B, 4096, 1024, 1);
        wg_fence();
#pragma unroll
        for (int i = 0; i < 4; i++) wgmma_n192(acc0, da + 2 * i, db + (i >> 1) * (STG1B >> 4) + (i & 1) * 128, 1);
        wg_commit();
        wg_wait<1>();
        if (wtid == 64) mbar_arrive(bars + 8 * (BAR_EMPTYB + NS1B - 1));
#pragma unroll
        for (int i = 0; i < 2; i++) wgmma_n192(acc1, da + 512 + 2 * i, db + (i >> 1) * (STG1B >> 4) + (i & 1) * 128, 1);
        wg_commit();
        wg_wait<1>();
        fence_regs(acc0);
        attn_stage(sb, blk0, lane, acc0, k1[0]);
#pragma unroll
        for (int i = 2; i < 4; i++) wgmma_n192(acc1, da + 512 + 2 * i, db + (i >> 1) * (STG1B >> 4) + (i & 1) * 128, 1);
        wg_commit();
        attn_pack(acc0, qa[0], k0[0]);
        wg_wait<0>();
        fence_regs(acc1);
      }
      if (wtid == 64) mbar_arrive(bars + 8 * BAR_EMPTYB);
      PROF(2 + wg);
      attn_stage(sb, blk0 + 4, lane, acc1, k1[1]);
      __syncwarp();
      if (lane == 0) mbar_arrive(bars + 8 * BAR_STG);
      mbar_wait(bars + 8 * BAR_U, 0);
      attn_pack(acc1, qa[1], k0[1]);
      attn_own(k0[0], k1[0], le0, le1, qa[0], l[0]);
      attn_own(k0[1], k1[1], le0, le1, qa[1], l[1]);
      const uint32_t cho[2] = {(uint32_t)(((lm & 1) ^ lr) << 4), (uint32_t)(((2 + (lm & 1)) ^ lr) << 4)};
      const uint32_t obase = sb + OFF_OP + (wg == (rb2 & 1) ? 16384 : 0) + ((warp & 3) * 16 + lr) * 128;
      mbar_wait(bars + 8 * BAR_T, 0);
      mbar_wait(bars + 8 * BAR_UH, 0);
      mbar_wait(bars + 8 * BAR_STG, 0);
      {
        uint32_t km[4][4], va[8][4], vb[8][4], pp[8];
        float x[8][2];
#pragma unroll
        for (int n = 0; n < 4; n++) {
          const int blk = blk0 + 4 * (n >> 1);
          to_arr(km[n], lds128(sb + (blk == 0 ? OFF_L0 + 1024 : OFF_KH + (blk - 1) * 2048) + (n & 1) * 512 + lane * 16));
        }
#pragma unroll
        for (int n = 0; n < 8; n++) {
          const int vr = (blk0 + 4 * ((n >> 1) & 1)) * 16 - 8 + 8 * (n >> 2) + 8 * (lm >> 1);
          const uint32_t vrow = sb + (vr < 0 ? OFF_L0 : OFF_VP + vr * 128) + lr * 128;
          ldsm4t(va[n], vrow + (cho[0] ^ ((n & 1) << 6)));
          ldsm4t(vb[n], vrow + (cho[1] ^ ((n & 1) << 6)));
        }
        to_arr(a1[0], lds128(tb + T_A1));
        to_arr(a1[1], lds128(tb + T_A1 + 2048));
        const bool first = blk0 == 0 && gidx == 0;
#pragma unroll
        for (int n = 0; n < 4; n++) {
          const uint32_t(&q)[8] = qa[n >> 1][n & 1];
          float sm[4];
          mma16816_z(sm, q[0], q[1], q[2], q[3], km[n][0], km[n][1]);
          mma16816(sm, q[4], q[5], q[6], q[7], km[n][2], km[n][3]);
          if (n < 2 && first) sm[0] = sm[1] = -1e9f / 0.17677669529663687f;
          x[n][0] = le0 ? l[n >> 1][n & 1][0] : sm[0];
          x[n][1] = le1 ? l[n >> 1][n & 1][1] : sm[1];
          x[4 + n][0] = l[n >> 1][n & 1][2];
          x[4 + n][1] = l[n >> 1][n & 1][3];
        }
#pragma unroll
        for (int n = 0; n < 4; n++) fence_regs(x[n]);
        wg_fence();
        s1(0);
        ldtw(0);
        ldtw(1);
        quad_softmax<8>(x, pp);
#pragma unroll
        for (int n = 7; n >= 0; n--)
          attn_pv(obase + ((n >> 1) & 1) * 8192 + (n >> 2) * 1024 + (((4 * (n & 1) + lm) ^ lr) << 4), va[n], vb[n], pp[n],
                  maskLE);
      }
      fence_async_smem();
      wg_wait<0>();
      fence_regs(d1);
      nb_sync(NB_OREADY + wg, 160);
    }

    {
      const int w = warp & 3;
      uint32_t a4[8][4];
      float d4[16];
      PROF(34 + wg);
      const uint64_t dz = mkdesc(sb + OFF_U + wg * 4096, 512, 128, 0);
      const uint64_t db2 = mkdesc(sb + OFF_T + T_B2, 128, 256, 0);
      const uint32_t za = sb + (w < 2 ? OFF_U : OFF_H) + wg * 4096 + (w & 1) * 2048 + lane * 16;
      const uint32_t yl = (wtid ^ (4 * rank + wg)) * 16;
      const uint32_t yown = mapa(sb, rank) + yl, yrem = mapa(sb + OFF_LAND + wg * 2048, rank ^ 1) + yl;
      const uint32_t yb[2] = {mapa(bars + 8 * BAR_LAND, 0), mapa(bars + 8 * BAR_LAND, 1)};
      auto s4 = [&](int it) {
        wg_fence();
#pragma unroll
        for (int ks = 0; ks < 8; ks++) {
          const uint64_t d = dz + (it & 1) * 512 + (ks & 3) * 64 + (ks >> 2) * ((OFF_H - OFF_U) >> 4);
          if (ks == 0) fmma_n32t<0>(d4, a4[ks], d);
          else fmma_n32t<1>(d4, a4[ks], d);
        }
        wg_commit();
      };
      auto e4 = [&](int it) {
        fence_regs(d4);
        const float sc = __uint_as_float(lds32(sb + OFF_SC + wg * 4 + it * 8));
        uint32_t r[8];
#pragma unroll
        for (int i = 0; i < 8; i++) r[i] = pack_bf16(d4[2 * i] * sc, d4[2 * i + 1] * sc);
        const uint32_t o = (yown + y_slot(wg, it)) ^ ((it >> 1) << 5), m = (yrem + it * 4096) ^ ((it >> 1) << 5);
        if (it == 0) mbar_wait(bars + 8 * BAR_LFREE, 0);
        if (it == 3) mbar_wait(bars + 8 * (BAR_DEAD + 1), 0);
        st_async128(rank ? m : o, yb[0], r[0], r[2], r[1], r[3]);
        st_async128(rank ? o : m, yb[1], r[4], r[6], r[5], r[7]);
      };
      uint32_t a2[2][2][2][4], a3[2][2][4], d2[2][2][8], d3[2][8];
      auto s2a = [&]() {
        wg_fence();
#pragma unroll
        for (int c = 0; c < 4; c++) hmma_n32<0, 0>(d2[c & 1][c >> 1], a2[0][c & 1][c >> 1], db2 + (c >> 1) * 128);
      };
      auto s2b = [&]() {
        wg_fence();
#pragma unroll
        for (int c = 0; c < 4; c++) {
          hmma_n32<1, 0>(d2[c & 1][c >> 1], a2[1][c & 1][c >> 1], db2 + (c >> 1) * 128 + 64);
          if (c & 1) wg_commit();
        }
      };
      auto done = [&](int it) {
        if (it == 0) {
          if (signaller) mbar_arrive_cluster(rbars + 8 * BAR_LFREE);
        } else if (it >= 2 && wtid == 64) {
          mbar_arrive(bars + 8 * (BAR_DEAD + it - 2));
        }
        if (w == 0) PROF3(40 + 4 * wg + it);
      };
      fft_e1<0>(d1, tw, a2[0]);
      s2a();
      fft_e1<1>(d1, tw, a2[1]);
      s2b();
      s1(1);
      ldtw(2);
      ldtw(3);
#pragma unroll
      for (int i = 0; i < 8; i++) to_arr(a4[i], lds128(tb + T_A4 + i * 2048));
#pragma unroll
      for (int it = 0; it < 4; it++) {
        if (it == 0 || it == 3) wg_wait<2>(); else wg_wait<3>();
        fence_regs(d2[0][0]);
        fence_regs(d2[1][0]);
        fft_e2<0, 0>(d2[0][0], d2[1][0], a3[0]);
        fft_e2<0, 1>(d2[0][0], d2[1][0], a3[1]);
        if (it == 0 || it == 3) wg_wait<1>(); else wg_wait<2>();
        fence_regs(d2[0][1]);
        fence_regs(d2[1][1]);
        fft_e2<1, 0>(d2[0][1], d2[1][1], a3[0]);
        fft_e2<1, 1>(d2[0][1], d2[1][1], a3[1]);
        wg_fence();
        hmma_n32<0, 0>(d3[0], a3[0][0], db2);
        hmma_n32<0, 0>(d3[1], a3[0][1], db2);
        hmma_n32<1, 0>(d3[0], a3[1][0], db2 + 64);
        hmma_n32<1, 0>(d3[1], a3[1][1], db2 + 64);
        wg_commit();
        wg_wait<1>();
        if (it > 0) e4(it - 1);
        if (it < 3) {
          fence_regs(d1);
          fft_e1<0>(d1, tw, a2[0]);
        }
        wg_wait<0>();
        fence_regs(d3[0]);
        fence_regs(d3[1]);
        if (it < 3) s2a();
        fft_e3(d3, tw, za + (it & 1) * 8192);
        if (it < 3) {
          fft_e1<1>(d1, tw, a2[1]);
          s2b();
        }
        fence_async_smem();
        nb_sync(NB_WG + wg, 128);
        done(it);
        s4(it);
        if (it < 2) s1(it + 2);
      }
      if (PEEL && MODE == 0) {
        mbar_wait(bars + 8 * BAR_FULL2, 0);
        g2_step(0, 0);
        wg_wait<1>();
      } else {
        wg_wait<0>();
      }
      if (signaller) mbar_arrive_cluster(rbars + 8 * (BAR_EMPTY2 + 4));
      e4(3);
      if (PEEL && MODE == 0) {
        wg_wait<0>();
        if (signaller) mbar_arrive_cluster(rbars + 8 * BAR_EMPTY2);
      }
      PROF(6 + wg);
    }
    }

    if (MODE != 1) {
      int s = PEEL && MODE == 0, ph = 0;
#pragma unroll 1
      for (int kb = s; kb < 16; kb++) {
        mbar_wait(bars + 8 * (BAR_FULL2 + s), ph);
        if (kb == 1) PROF(8 + wg);
        if (warp == 4) PROF2(40 + kb);
        g2_step(s, kb);
        wg_wait<0>();
        if (kb < 16 - NS2 && signaller) mbar_arrive_cluster(rbars + 8 * (BAR_EMPTY2 + s));
        if (++s == NS2) { s = 0; ph ^= 1; }
      }
      wg_wait<0>();
      fence_regs(acc);
      PROF(10 + wg);
      const int lr = lane & 7, lm = lane >> 3;
      const uint32_t wbase = sb + warp * 2048;
      const uint32_t base = wbase + (lr + 8 * (lm & 1)) * 128;
#pragma unroll
      for (int j = 0; j < 16; j += 2) {
        const uint32_t a = base + (j >> 3) * 16384 + ((((j & 7) + (lm >> 1)) ^ lr) << 4);
        stsm4(a, pack_bf16(acc[4 * j], acc[4 * j + 1]), pack_bf16(acc[4 * j + 2], acc[4 * j + 3]),
              pack_bf16(acc[4 * j + 4], acc[4 * j + 5]), pack_bf16(acc[4 * j + 6], acc[4 * j + 7]));
      }
      __syncwarp();
      {
        const int rr = lane >> 4, ck = lane & 7, hf = (lane >> 3) & 1;
        uint4* og = reinterpret_cast<uint4*>(p.out + (size_t)(2 * ((rb2 & 7) * 128 + warp * 16 + rr) + (rb2 >> 3)) * (2 * DM) + DM + cb2 * 128 + hf * 64 + ck * 8);
        uint4 v[8];
#pragma unroll
        for (int i = 0; i < 8; i++) v[i] = lds128(wbase + hf * 16384 + (2 * i + rr) * 128 + ((ck ^ ((2 * i + rr) & 7)) << 4));
#pragma unroll
        for (int i = 0; i < 8; i++) og[(size_t)i * 4 * (2 * DM / 8)] = v[i];
      }
      PROF(12 + wg);
    }
    cluster_sync_all();
  }
}

typedef CUresult (*EncodeFn)(CUtensorMap*, CUtensorMapDataType, cuuint32_t, void*, const cuuint64_t*, const cuuint64_t*,
                             const cuuint32_t*, const cuuint32_t*, CUtensorMapInterleave, CUtensorMapSwizzle,
                             CUtensorMapL2promotion, CUtensorMapFloatOOBfill);

void make_map(EncodeFn enc, CUtensorMap* tm, const void* base, int rank, const cuuint64_t* dims, const cuuint64_t* strides,
              const cuuint32_t* box, CUtensorMapSwizzle swz) {
  cuuint32_t es[5] = {1, 1, 1, 1, 1};
  enc(tm, CU_TENSOR_MAP_DATA_TYPE_BFLOAT16, rank, const_cast<void*>(base), dims, strides, box, es,
      CU_TENSOR_MAP_INTERLEAVE_NONE, swz, CU_TENSOR_MAP_L2_PROMOTION_L2_256B, CU_TENSOR_MAP_FLOAT_OOB_FILL_NONE);
}

}

extern "C" void kernel_launch(void* const* d_in, const int* in_sizes, int n_in, void* d_out, int out_size) {
  static EncodeFn enc = nullptr;
  static bool coresident = true;
  if (!enc) {
    void* fn = nullptr;
    cudaDriverEntryPointQueryResult qr;
    cudaGetDriverEntryPoint("cuTensorMapEncodeTiled", &fn, cudaEnableDefault, &qr);
    enc = (EncodeFn)fn;
    cudaFuncSetAttribute(fused_kernel<0>, cudaFuncAttributeMaxDynamicSharedMemorySize, SMEM_BYTES);
    cudaFuncSetAttribute(fused_kernel<1>, cudaFuncAttributeMaxDynamicSharedMemorySize, SMEM_BYTES);
    cudaFuncSetAttribute(fused_kernel<2>, cudaFuncAttributeMaxDynamicSharedMemorySize, SMEM_BYTES);
    cudaLaunchConfig_t cfg = {};
    cfg.gridDim = dim3(NCTA);
    cfg.blockDim = dim3(NTHREADS);
    cfg.dynamicSmemBytes = SMEM_BYTES;
    cudaLaunchAttribute at;
    at.id = cudaLaunchAttributeClusterDimension;
    at.val.clusterDim.x = 2;
    at.val.clusterDim.y = 1;
    at.val.clusterDim.z = 1;
    cfg.attrs = &at;
    cfg.numAttrs = 1;
    int nclusters = 0;
    if (cudaOccupancyMaxActiveClusters(&nclusters, fused_kernel<0>, &cfg) == cudaSuccess) coresident = nclusters >= NCTA / 2;
    (void)cudaGetLastError();
  }
  CUtensorMap tmX, tmW, tmWo, tmQ, tmXh, tmWh;
  {
    cuuint64_t dims[3] = {1024, 2, 1024};
    cuuint64_t str[2] = {2048, 4096};
    cuuint32_t box[3] = {64, 1, 128};
    make_map(enc, &tmX, d_in[6], 3, dims, str, box, CU_TENSOR_MAP_SWIZZLE_128B);
  }
  {
    cuuint64_t dims[3] = {1024, 1024, 3};
    cuuint64_t str[2] = {6144, 2048};
    cuuint32_t box[3] = {64, 32, 3};
    make_map(enc, &tmW, d_in[7], 3, dims, str, box, CU_TENSOR_MAP_SWIZZLE_128B);
  }
  {
    cuuint64_t dims[3] = {64, 1024, 16};
    cuuint64_t str[2] = {2048, 128};
    cuuint32_t box[3] = {64, 64, 2};
    make_map(enc, &tmWo, d_in[8], 3, dims, str, box, CU_TENSOR_MAP_SWIZZLE_128B);
  }
  {
    cuuint64_t dims[5] = {1024, 2, 4, 4, 64};
    cuuint64_t str[4] = {2048, 8 * 2048, 2 * 2048, 32 * 2048};
    cuuint32_t box[5] = {16, 2, 4, 4, 4};
    make_map(enc, &tmQ, d_in[0], 5, dims, str, box, CU_TENSOR_MAP_SWIZZLE_NONE);
  }
  {
    cuuint64_t dims[4] = {1024, 256, 2, 4};
    cuuint64_t str[3] = {4096, 2048, 256 * 4096};
    cuuint32_t box[4] = {64, 8, 2, 4};
    make_map(enc, &tmXh, d_in[6], 4, dims, str, box, CU_TENSOR_MAP_SWIZZLE_128B);
  }
  {
    cuuint64_t dims[3] = {64, 1024, 48};
    cuuint64_t str[2] = {6144, 128};
    cuuint32_t box[3] = {64, 64, 4};
    make_map(enc, &tmWh, d_in[7], 3, dims, str, box, CU_TENSOR_MAP_SWIZZLE_128B);
  }
  Params p;
  p.q = (const __nv_bfloat16*)d_in[0];
  p.k = (const __nv_bfloat16*)d_in[1];
  p.v = (const __nv_bfloat16*)d_in[2];
  p.shift_k = (const __nv_bfloat16*)d_in[3];
  p.ssm_k = (const __nv_bfloat16*)d_in[4];
  p.ssm_D = (const __nv_bfloat16*)d_in[5];
  p.x = (const __nv_bfloat16*)d_in[6];
  p.w = (const __nv_bfloat16*)d_in[7];
  p.wo = (const __nv_bfloat16*)d_in[8];
  p.out = (__nv_bfloat16*)d_out;
  if (coresident) {
    fused_kernel<0><<<NCTA, NTHREADS, SMEM_BYTES>>>(p, tmX, tmW, tmWo, tmQ, tmXh, tmWh);
  } else {
    fused_kernel<0><<<4, NTHREADS, SMEM_BYTES>>>(p, tmX, tmW, tmWo, tmQ, tmXh, tmWh);
    fused_kernel<1><<<NCTA, NTHREADS, SMEM_BYTES>>>(p, tmX, tmW, tmWo, tmQ, tmXh, tmWh);
    fused_kernel<2><<<NCTA, NTHREADS, SMEM_BYTES>>>(p, tmX, tmW, tmWo, tmQ, tmXh, tmWh);
  }
}
```

```cpp
#include <cuda_runtime.h>
#include <cuda.h>
#include <cuda_bf16.h>
#include <stdint.h>

namespace {

constexpr int SEQ = 2048;
constexpr int DM = 1024;
constexpr int NCTA = 132;
constexpr int NTHREADS = 384;

constexpr int STG1A = 32768;
constexpr int NS1A = 3;
constexpr int STG1B = 12288;
constexpr int NS1B = 5;
constexpr int OFF_1B = NS1A * STG1A;
constexpr int STG2 = 32768;
constexpr int NS2 = 5;
constexpr int STGH = 73728;
constexpr int OFF_VP = 0;
constexpr int OFF_KH = 1 * STG2;
constexpr int OFF_OP = 2 * STG2;
constexpr int OFF_Q = 3 * STG2;
constexpr int T_A4 = 0, T_TW = 16384, T_B2 = 24576, T_A1 = 28672, T_END = 32768;
constexpr int OFF_U = 163840;
constexpr int OFF_H = OFF_U + 32768;
constexpr int OFF_T = OFF_U - T_END;
constexpr int OFF_LAND = 4 * STG2;
constexpr int OFF_BAR = OFF_H + 32768;
constexpr int OFF_SC = OFF_BAR + 512;
constexpr int OFF_L0 = OFF_BAR + 1024;
constexpr int SMEM_BYTES = OFF_L0 + 2048;
static_assert(OFF_T + T_A1 == OFF_1B + NS1B * STG1B && OFF_T + T_TW == OFF_1B + 4 * STG1B && OFF_LAND == OFF_T + T_A4, "layout");
static_assert(3 * STGH <= OFF_BAR && SMEM_BYTES <= 232448, "smem");

constexpr int BAR_FULLA = 0;
constexpr int BAR_EMPTYA = 3;
constexpr int BAR_FULLB = 6;
constexpr int BAR_EMPTYB = 11;
constexpr int BAR_FULL2 = 16;
constexpr int BAR_EMPTY2 = 21;
constexpr int BAR_T = 26;
constexpr int BAR_UH = 27;
constexpr int BAR_LFREE = 28;
constexpr int BAR_LAND = 29;
constexpr int BAR_U = 30;
constexpr int BAR_Q = 31;
constexpr int BAR_STG = 32;
constexpr int BAR_DEAD = 33;
constexpr int BAR_X = 35;
constexpr int BAR_REL = 36;

constexpr int NB_G1DONE = 1;
constexpr int NB_OREADY = 2;
constexpr int NB_WG = 4;
constexpr int NB_HELP3 = 6;
constexpr int NB_FIRST = 7;

#define PACE 480u
#define PF0 20
#define EARLYS1 0
#define PEEL 1
#define IDLEW 1
#define SCHED 1
#define REG_MATH 224
#define REG_HELP 56
constexpr int SPIN_LIMIT = 1 << 20;

__device__ __align__(1024) __nv_bfloat16 g_o[SEQ * DM];
__device__ uint32_t g_flag_o[256];
__device__ uint32_t g_flag_h[4];
__device__ uint4 g_halo[128 * 128];
__device__ __align__(128) const uint32_t g_tab[T_END / 4] = {
0x3c003c00,0x3bf13bff,0,0xafd6a648,0x3c003c00,0x3b993bce,0,0xb505b303,0x3c003c00,0x3af63b50,0,0xb7e3b67c,
0x3c003c00,0x3a0f3a8a,0,0xb93ab89b,0x3bc33bfe,0x3b773bfa,0xb3c6aa48,0xb5c2acb5,0x3a6d3b3b,0x389b3a4f,0xb8c4b6d7,0xba8ab8ec,
0x381d395f,0x26483505,0xbaddb9ed,0xbbffbb99,0x30b23564,0xb848b444,0xbbeabb88,0xbac2bbb6,0x3b0e3bf6,0x3a8a3bf1,0xb78bae46,0xb89bafd6,
0x34a53913,0xa6483732,0xbba8ba2f,0xbbffbb25,0xb78bae46,0xbac2b7e3,0xbb0ebbf6,0xb848baf6,0xbba8ba2f,0xbb50bbfa,0xb4a5b913,0x367cacb5,
0x39ed3bea,0x393a3be2,0xb95fb0b2,0xba0fb179,0xb56433c6,0xb8ec2648,0xbb88bbc3,0xba4fbbff,0xbbfeba6d,0xbb25bbce,0xaa48b8c4,0x3732b303,
0xb6d7badd,0x3444b67c,0x3b3b381d,0x3bb63b50,0x38723bd9,0x37323bce,0xbaa7b23e,0xbb25b303,0xbaa7b23e,0xbbb6b67c,0xb872bbd9,0xb444bb50,
0xb872bbd9,0xacb5ba8a,0x3aa7323e,0x3bfa389b,0x3aa7323e,0x3bf139cb,0x38723bd9,0xafd63984,0x35643bc3,0x33033bb6,0xbb88b3c6,0xbbceb444,
0xbbfeb8c4,0xbb77ba0f,0x2a48ba6d,0x35c2b93a,0x36d7b81d,0x3a8aafd6,0x3b3b3add,0x389b3bf1,0x395f3bea,0x26483b25,0xb9ed30b2,0xbbffb732,
0x2e463ba8,0xa6483b99,0xbbf6b4a5,0xbbffb505,0xba2fbb0e,0xb848bbb6,0x3913b78b,0x3ac2b444,0x3bf634a5,0x3b50393a,0x2e463ba8,0xb67c3a0f,
0xb913378b,0xbbe2afd6,0xba2fbb0e,0xb179bbf1,0xb0b23b88,0xb4443b77,0xbbeab564,0xbbb6b5c2,0xb3c6bbfe,0x2cb5bbe2,0x3bc3aa48,0x3bfa3179,
0x38c43b3b,0x2fd63bff,0xba6d36d7,0xbbf12648,0xbaddb95f,0xb505bbce,0x381db9ed,0x3b99b303,0xb61f3b64,0xb7e33b50,0xbb64b61f,0xbaf6b67c,
0x361fbb64,0x393aba8a,0x3b64361f,0x3a0f389b,0xb61f3b64,0xba4f3984,0xbb64b61f,0xb8ecb9cb,0x361fbb64,0x3b25b848,0x3b64361f,0x37323ac2,
0xb8c43b3b,0xb9843b25,0xba6db6d7,0xb9cbb732,0x3addb95f,0x3bceb7e3,0x381d39ed,0x33033af6,0xbbea3564,0xbb77acb5,0xb0b2bb88,0x35c2bbfa,
0x3bc32a48,0x389b38ec,0xb3c63bfe,0xba8a3a4f,0xba2f3b0e,0xbac23af6,0xb913b78b,0xb848b7e3,0x3bf6b4a5,0x3b50acb5,0xae463ba8,0xb67c3bfa,
0xb913b78b,0xb179ba4f,0x3a2fbb0e,0x3be2b8ec,0xae463ba8,0xb9cb3b99,0xbbf634a5,0xb984b505,0xbb3b3add,0xbb993ac2,0xb6d7b81d,0xb505b848,
0x39ed30b2,0x37e335c2,0xb95f3bea,0xbaf63b77,0x3564bbc3,0x3a0fbbe2,0x3b88b3c6,0x393a3179,0xbbfe38c4,0xba4f2648,0xaa48ba6d,0x38ecbbff,
0xbbd93aa7,0xbbfa3a8a,0xb23eb872,0xacb5b89b,0x323e3872,0xafd639cb,0xbbd93aa7,0xbbf13984,0x3bd9baa7,0x3b99b848,0x323e3872,0xb5053ac2,
0xb23eb872,0x37e3bb77,0x3bd9baa7,0x3af6b5c2,0xbbfe3a6d,0xbbe23a4f,0x2a48b8c4,0x3179b8ec,0xb6d73add,0xb9843b99,0xbb3b381d,0xb9cb3505,
0x395fb0b2,0x33033444,0xb9ed3bea,0xbbce3bb6,0x3b88bbc3,0x3b77b93a,0x356433c6,0xb5c23a0f,0xbba83a2f,0xbb503a0f,0x34a5b913,0x367cb93a,
0xbb0e3bf6,0xbbe23bf1,0xb78b2e46,0xb179afd6,0xb4a53913,0xb9cb3b25,0xbba83a2f,0xb9843732,0x378bae46,0xb30337e3,0xbb0e3bf6,0xbbce3af6,
0xbadd39ed,0xba4f39cb,0x381db95f,0x38ecb984,0xbbea3b88,0xbb253ac2,0x30b2b564,0x3732b848,0xbbc33bfe,0xbbb63b77,0xb3c62a48,0x3444b5c2,
0xba6d3b3b,0xbbfa3be2,0xb8c436d7,0x2cb5b179,0xb9a839a8,0xb8ec3984,0x39a8b9a8,0x3a4fb9cb,0xb9a839a8,0xb7323848,0x39a8b9a8,0x3b25bac2,
0xb9a839a8,0xb44435c2,0x39a8b9a8,0x3bb6bb77,0xb9a839a8,0xacb53179,0x39a8b9a8,0x3bfabbe2,0xb81d395f,0xb67c393a,0x3addb9ed,0x3b50ba0f,
0xb0b23564,0x31792fd6,0x3beabb88,0x3be2bbf1,0x33c6aa48,0x3984b732,0x3bc3bbfe,0x39cbbb25,0x38c4b6d7,0x3bcebaf6,0x3a6dbb3b,0x3303b7e3,
0xb4a53913,0xb17938ec,0x3ba8ba2f,0x3be2ba4f,0x378bae46,0x39cbb505,0x3b0ebbf6,0x3984bb99,0x3ba8ba2f,0x3bcebbb6,0x34a5b913,0xb303b444,
0x3b0ebbf6,0x35c2ba0f,0xb78b2e46,0xbb77393a,0xaa4838c4,0x2cb5389b,0x3bfeba6d,0x3bfaba8a,0x3b3bb81d,0x3bf1b984,0x36d7badd,0x2fd6b9cb,
0x39edbbea,0x3505bac2,0xb95f30b2,0xbb993848,0xb564b3c6,0xbaf635c2,0xbb883bc3,0xb7e33b77,0x323e3872,0x35053848,0x3bd9baa7,0x3b99bac2,
0x3bd9baa7,0x3af6bb77,0xb23eb872,0xb7e3b5c2,0xb23eb872,0xb93ab179,0xbbd93aa7,0xba0f3be2,0xbbd93aa7,0xb8ec3bff,0x323e3872,0x3a4fa648,
0x36d7381d,0x384837e3,0x3b3bbadd,0x3ac2baf6,0x395fbbea,0x367cbbfa,0xb9edb0b2,0xbb502cb5,0xbb8833c6,0xbbe238ec,0xb5643bc3,0x31793a4f,
0x2a483a6d,0x39843505,0x3bfeb8c4,0x39cbbb99,0x3913378b,0x39cb3732,0x3a2fbb0e,0x3984bb25,0x2e46bba8,0xb303baf6,0xbbf634a5,0xbbce37e3,
0xba2f3b0e,0xb5c23bfa,0x3913378b,0x3b772cb5,0x3bf6b4a5,0x3a8aba4f,0x2e46bba8,0xb89bb8ec,0x3a6d36d7,0x3af6367c,0x38c4bb3b,0x37e3bb50,
0xb81db9ed,0xba0fb89b,0xbadd395f,0xb93a3a8a,0x30b23b88,0x38ec39cb,0x3beab564,0x3a4fb984,0x33c6bbfe,0xb732bac2,0xbbc3aa48,0xbb253848,
0x3b64361f,0x3bb635c2,0x361fbb64,0x3444bb77,0xbb64b61f,0xbbfab179,0xb61f3b64,0xacb53be2,0x3b64361f,0x3bf1a648,0x361fbb64,0xafd6bbff,
0xbb64b61f,0xbb993303,0xb61f3b64,0x35053bce,0x3bea3564,0x3bff3505,0x30b2bb88,0x2648bb99,0xbbc32a48,0xbac23444,0x33c63bfe,0x38483bb6,
0x3a6db6d7,0x367cba0f,0xb8c4bb3b,0xbb50b93a,0xb81d39ed,0x31793bf1,0x3add395f,0x3be22fd6,0x3bf634a5,0x3bce3444,0xae46bba8,0xb303bbb6,
0xb913378b,0xb5c2393a,0x3a2f3b0e,0x3b773a0f,0xae46bba8,0xb89bbbf1,0xbbf6b4a5,0xba8a2fd6,0x3a2f3b0e,0x3bff3732,0x3913b78b,0xa648bb25,
0x3b8833c6,0x3b253303,0xb564bbc3,0xb732bbce,0xaa483a6d,0x34443b50,0x3bfe38c4,0x3bb6367c,0xbb3bbadd,0xbbfab89b,0xb6d7381d,0x2cb53a8a,
0x39edb0b2,0x2fd6b984,0xb95fbbea,0xbbf1b9cb,0x3aa7323e,0x3a0f3179,0xb872bbd9,0xb93abbe2,0x38723bd9,0x3a4f3bff,0x3aa7323e,0x38eca648,
0xbaa7b23e,0xb7323303,0x38723bd9,0x3b253bce,0xb872bbd9,0xbbb6bb50,0xbaa7b23e,0xb444367c,0x395f30b2,0x389b2fd6,0xb9edbbea,0xba8abbf1,
0x3b883bc3,0x3bff3b25,0x3564b3c6,0x2648b732,0x2a4838c4,0x38483af6,0x3bfe3a6d,0x3ac237e3,0xbb3bb81d,0xb67c2cb5,0x36d73add,0x3b503bfa,
0x378b2e46,0x35c22cb5,0xbb0ebbf6,0xbb77bbfa,0x3ba83a2f,0x3a8a38ec,0xb4a5b913,0xb89bba4f,0x3b0e3bf6,0x3bff3b99,0x378b2e46,0xa648b505,
0x34a53913,0x3ac23bb6,0x3ba83a2f,0x38483444,0x33c62a48,0x2fd62648,0xbbc3bbfe,0xbbf1bbff,0x38c436d7,0x35053303,0xba6dbb3b,0xbb99bbce,
0x3add39ed,0x37e3367c,0xb81db95f,0xbaf6bb50,0x3bea3b88,0x393a389b,0xb0b2b564,0xba0fba8a,0x3c003c00,0xbbf1bbff,0,0x2fd62648,
0x3c003c00,0xbb99bbce,0,0x35053303,0x3c003c00,0xbaf6bb50,0,0x37e3367c,0x3c003c00,0xba0fba8a,0,0x393a389b,
0x3bc33bfe,0xbb77bbfa,0xb3c6aa48,0x35c22cb5,0x3a6d3b3b,0xb89bba4f,0xb8c4b6d7,0x3a8a38ec,0x381d395f,0xa648b505,0xbaddb9ed,0x3bff3b99,
0x30b23564,0x38483444,0xbbeabb88,0x3ac23bb6,0x3b0e3bf6,0xba8abbf1,0xb78bae46,0x389b2fd6,0x34a53913,0x2648b732,0xbba8ba2f,0x3bff3b25,
0xb78bae46,0x3ac237e3,0xbb0ebbf6,0x38483af6,0xbba8ba2f,0x3b503bfa,0xb4a5b913,0xb67c2cb5,0x39ed3bea,0xb93abbe2,0xb95fb0b2,0x3a0f3179,
0xb56433c6,0x38eca648,0xbb88bbc3,0x3a4f3bff,0xbbfeba6d,0x3b253bce,0xaa48b8c4,0xb7323303,0xb6d7badd,0xb444367c,0x3b3b381d,0xbbb6bb50,
0x38723bd9,0xb732bbce,0xbaa7b23e,0x3b253303,0xbaa7b23e,0x3bb6367c,0xb872bbd9,0x34443b50,0xb872bbd9,0x2cb53a8a,0x3aa7323e,0xbbfab89b,
0x3aa7323e,0xbbf1b9cb,0x38723bd9,0x2fd6b984,0x35643bc3,0xb303bbb6,0xbb88b3c6,0x3bce3444,0xbbfeb8c4,0x3b773a0f,0x2a48ba6d,0xb5c2393a,
0x36d7b81d,0xba8a2fd6,0x3b3b3add,0xb89bbbf1,0x395f3bea,0xa648bb25,0xb9ed30b2,0x3bff3732,0x2e463ba8,0x2648bb99,0xbbf6b4a5,0x3bff3505,
0xba2fbb0e,0x38483bb6,0x3913b78b,0xbac23444,0x3bf634a5,0xbb50b93a,0x2e463ba8,0x367cba0f,0xb913378b,0x3be22fd6,0xba2fbb0e,0x31793bf1,
0xb0b23b88,0x3444bb77,0xbbeab564,0x3bb635c2,0xb3c6bbfe,0xacb53be2,0x3bc3aa48,0xbbfab179,0x38c43b3b,0xafd6bbff,0xba6d36d7,0x3bf1a648,
0xbaddb95f,0x35053bce,0x381db9ed,0xbb993303,0xb61f3b64,0x37e3bb50,0xbb64b61f,0x3af6367c,0x361fbb64,0xb93a3a8a,0x3b64361f,0xba0fb89b,
0xb61f3b64,0x3a4fb984,0xbb64b61f,0x38ec39cb,0x361fbb64,0xbb253848,0x3b64361f,0xb732bac2,0xb8c43b3b,0x3984bb25,0xba6db6d7,0x39cb3732,
0x3addb95f,0xbbce37e3,0x381d39ed,0xb303baf6,0xbbea3564,0x3b772cb5,0xb0b2bb88,0xb5c23bfa,0x3bc32a48,0xb89bb8ec,0xb3c63bfe,0x3a8aba4f,
0xba2f3b0e,0x3ac2baf6,0xb913b78b,0x384837e3,0x3bf6b4a5,0xbb502cb5,0xae463ba8,0x367cbbfa,0xb913b78b,0x31793a4f,0x3a2fbb0e,0xbbe238ec,
0xae463ba8,0x39cbbb99,0xbbf634a5,0x39843505,0xbb3b3add,0x3b99bac2,0xb6d7b81d,0x35053848,0x39ed30b2,0xb7e3b5c2,0xb95f3bea,0x3af6bb77,
0x3564bbc3,0xba0f3be2,0x3b88b3c6,0xb93ab179,0xbbfe38c4,0x3a4fa648,0xaa48ba6d,0xb8ec3bff,0xbbd93aa7,0x3bfaba8a,0xb23eb872,0x2cb5389b,
0x323e3872,0x2fd6b9cb,0xbbd93aa7,0x3bf1b984,0x3bd9baa7,0xbb993848,0x323e3872,0x3505bac2,0xb23eb872,0xb7e33b77,0x3bd9baa7,0xbaf635c2,
0xbbfe3a6d,0x3be2ba4f,0x2a48b8c4,0xb17938ec,0xb6d73add,0x3984bb99,0xbb3b381d,0x39cbb505,0x395fb0b2,0xb303b444,0xb9ed3bea,0x3bcebbb6,
0x3b88bbc3,0xbb77393a,0x356433c6,0x35c2ba0f,0xbba83a2f,0x3b50ba0f,0x34a5b913,0xb67c393a,0xbb0e3bf6,0x3be2bbf1,0xb78b2e46,0x31792fd6,
0xb4a53913,0x39cbbb25,0xbba83a2f,0x3984b732,0x378bae46,0x3303b7e3,0xbb0e3bf6,0x3bcebaf6,0xbadd39ed,0x3a4fb9cb,0x381db95f,0xb8ec3984,
0xbbea3b88,0x3b25bac2,0x30b2b564,0xb7323848,0xbbc33bfe,0x3bb6bb77,0xb3c62a48,0xb44435c2,0xba6d3b3b,0x3bfabbe2,0xb8c436d7,0xacb53179,
0xb9a839a8,0x38ecb984,0x39a8b9a8,0xba4f39cb,0xb9a839a8,0x3732b848,0x39a8b9a8,0xbb253ac2,0xb9a839a8,0x3444b5c2,0x39a8b9a8,0xbbb63b77,
0xb9a839a8,0x2cb5b179,0x39a8b9a8,0xbbfa3be2,0xb81d395f,0x367cb93a,0x3addb9ed,0xbb503a0f,0xb0b23564,0xb179afd6,0x3beabb88,0xbbe23bf1,
0x33c6aa48,0xb9843732,0x3bc3bbfe,0xb9cb3b25,0x38c4b6d7,0xbbce3af6,0x3a6dbb3b,0xb30337e3,0xb4a53913,0x3179b8ec,0x3ba8ba2f,0xbbe23a4f,
0x378bae46,0xb9cb3505,0x3b0ebbf6,0xb9843b99,0x3ba8ba2f,0xbbce3bb6,0x34a5b913,0x33033444,0x3b0ebbf6,0xb5c23a0f,0xb78b2e46,0x3b77b93a,
0xaa4838c4,0xacb5b89b,0x3bfeba6d,0xbbfa3a8a,0x3b3bb81d,0xbbf13984,0x36d7badd,0xafd639cb,0x39edbbea,0xb5053ac2,0xb95f30b2,0x3b99b848,
0xb564b3c6,0x3af6b5c2,0xbb883bc3,0x37e3bb77,0x323e3872,0xb505b848,0x3bd9baa7,0xbb993ac2,0x3bd9baa7,0xbaf63b77,0xb23eb872,0x37e335c2,
0xb23eb872,0x393a3179,0xbbd93aa7,0x3a0fbbe2,0xbbd93aa7,0x38ecbbff,0x323e3872,0xba4f2648,0x36d7381d,0xb848b7e3,0x3b3bbadd,0xbac23af6,
0x395fbbea,0xb67c3bfa,0xb9edb0b2,0x3b50acb5,0xbb8833c6,0x3be2b8ec,0xb5643bc3,0xb179ba4f,0x2a483a6d,0xb984b505,0x3bfeb8c4,0xb9cb3b99,
0x3913378b,0xb9cbb732,0x3a2fbb0e,0xb9843b25,0x2e46bba8,0x33033af6,0xbbf634a5,0x3bceb7e3,0xba2f3b0e,0x35c2bbfa,0x3913378b,0xbb77acb5,
0x3bf6b4a5,0xba8a3a4f,0x2e46bba8,0x389b38ec,0x3a6d36d7,0xbaf6b67c,0x38c4bb3b,0xb7e33b50,0xb81db9ed,0x3a0f389b,0xbadd395f,0x393aba8a,
0x30b23b88,0xb8ecb9cb,0x3beab564,0xba4f3984,0x33c6bbfe,0x37323ac2,0xbbc3aa48,0x3b25b848,0x3b64361f,0xbbb6b5c2,0x361fbb64,0xb4443b77,
0xbb64b61f,0x3bfa3179,0xb61f3b64,0x2cb5bbe2,0x3b64361f,0xbbf12648,0x361fbb64,0x2fd63bff,0xbb64b61f,0x3b99b303,0xb61f3b64,0xb505bbce,
0x3bea3564,0xbbffb505,0x30b2bb88,0xa6483b99,0xbbc32a48,0x3ac2b444,0x33c63bfe,0xb848bbb6,0x3a6db6d7,0xb67c3a0f,0xb8c4bb3b,0x3b50393a,
0xb81d39ed,0xb179bbf1,0x3add395f,0xbbe2afd6,0x3bf634a5,0xbbceb444,0xae46bba8,0x33033bb6,0xb913378b,0x35c2b93a,0x3a2f3b0e,0xbb77ba0f,
0xae46bba8,0x389b3bf1,0xbbf6b4a5,0x3a8aafd6,0x3a2f3b0e,0xbbffb732,0x3913b78b,0x26483b25,0x3b8833c6,0xbb25b303,0xb564bbc3,0x37323bce,
0xaa483a6d,0xb444bb50,0x3bfe38c4,0xbbb6b67c,0xbb3bbadd,0x3bfa389b,0xb6d7381d,0xacb5ba8a,0x39edb0b2,0xafd63984,0xb95fbbea,0x3bf139cb,
0x3aa7323e,0xba0fb179,0xb872bbd9,0x393a3be2,0x38723bd9,0xba4fbbff,0x3aa7323e,0xb8ec2648,0xbaa7b23e,0x3732b303,0x38723bd9,0xbb25bbce,
0xb872bbd9,0x3bb63b50,0xbaa7b23e,0x3444b67c,0x395f30b2,0xb89bafd6,0xb9edbbea,0x3a8a3bf1,0x3b883bc3,0xbbffbb25,0x3564b3c6,0xa6483732,
0x2a4838c4,0xb848baf6,0x3bfe3a6d,0xbac2b7e3,0xbb3bb81d,0x367cacb5,0x36d73add,0xbb50bbfa,0x378b2e46,0xb5c2acb5,0xbb0ebbf6,0x3b773bfa,
0x3ba83a2f,0xba8ab8ec,0xb4a5b913,0x389b3a4f,0x3b0e3bf6,0xbbffbb99,0x378b2e46,0x26483505,0x34a53913,0xbac2bbb6,0x3ba83a2f,0xb848b444,
0x33c62a48,0xafd6a648,0xbbc3bbfe,0x3bf13bff,0x38c436d7,0xb505b303,0xba6dbb3b,0x3b993bce,0x3add39ed,0xb7e3b67c,0xb81db95f,0x3af63b50,
0x3bea3b88,0xb93ab89b,0xb0b2b564,0x3a0f3a8a,0x3c003c00,0x38ec3984,0,0xba4fb9cb,0x3c003c00,0x37323848,0,0xbb25bac2,
0x3c003c00,0x344435c2,0,0xbbb6bb77,0x3c003c00,0x2cb53179,0,0xbbfabbe2,0xb3c6aa48,0xbb50ba0f,0xbbc3bbfe,0xb67cb93a,
0xb8c4b6d7,0xbbe2bbf1,0xba6dbb3b,0x3179afd6,0xbaddb9ed,0xb9cbbb25,0xb81db95f,0x39843732,0xbbeabb88,0xb303b7e3,0xb0b2b564,0x3bce3af6,
0xbb0ebbf6,0xb179b8ec,0x378b2e46,0x3be23a4f,0xb4a5b913,0x39cb3505,0x3ba83a2f,0x39843b99,0x378b2e46,0x3bce3bb6,0x3b0e3bf6,0xb3033444,
0x3ba83a2f,0x35c23a0f,0x34a53913,0xbb77b93a,0x395f30b2,0x3bfa3a8a,0x39ed3bea,0xacb5389b,0x3b883bc3,0x2fd639cb,0xb56433c6,0xbbf1b984,
0x2a4838c4,0xbb99b848,0xbbfeba6d,0xb505bac2,0xbb3bb81d,0xb7e3bb77,0xb6d7badd,0x3af635c2,0x38723bd9,0xb5053848,0xbaa7b23e,0xbb99bac2,
0xbaa7b23e,0xbaf6bb77,0xb872bbd9,0x37e3b5c2,0xb872bbd9,0x393ab179,0x3aa7323e,0x3a0f3be2,0x3aa7323e,0x38ec3bff,0x38723bd9,0xba4fa648,
0xbb88b3c6,0xbac2baf6,0xb564bbc3,0x3848b7e3,0x2a48ba6d,0x3b502cb5,0x3bfe38c4,0x367c3bfa,0x3b3b3add,0xb1793a4f,0xb6d7381d,0xbbe2b8ec,
0xb9ed30b2,0xb9cbbb99,0xb95fbbea,0x3984b505,0xae46bba8,0x39cbb732,0x3bf634a5,0x39843b25,0x3a2f3b0e,0xb3033af6,0xb913378b,0xbbceb7e3,
0xbbf6b4a5,0xb5c2bbfa,0xae46bba8,0x3b77acb5,0x3913b78b,0x3a8a3a4f,0x3a2f3b0e,0xb89b38ec,0x3bea3564,0x37e33b50,0xb0b23b88,0xbaf6367c,
0xbbc32a48,0xb93aba8a,0xb3c6bbfe,0x3a0fb89b,0x3a6db6d7,0x3a4f3984,0x38c43b3b,0xb8ec39cb,0xb81d39ed,0xbb25b848,0xbaddb95f,0x3732bac2,
0xb61f3b64,0xbbb635c2,0xbb64b61f,0xb444bb77,0x361fbb64,0x3bfab179,0x3b64361f,0x2cb53be2,0xb61f3b64,0xbbf1a648,0xbb64b61f,0x2fd6bbff,
0x361fbb64,0x3b993303,0x3b64361f,0xb5053bce,0xba6db6d7,0xa648bb99,0x38c4bb3b,0x3bffb505,0x381d39ed,0xb8483bb6,0xbadd395f,0xbac2b444,
0xb0b2bb88,0x3b50b93a,0x3beab564,0x367c3a0f,0xb3c63bfe,0xbbe22fd6,0xbbc3aa48,0x3179bbf1,0x3a2fbb0e,0x3bceb444,0x3913378b,0xb3033bb6,
0xbbf634a5,0xb5c2b93a,0x2e46bba8,0x3b77ba0f,0x3913378b,0xb89b3bf1,0xba2f3b0e,0xba8aafd6,0x2e46bba8,0x3bffb732,0x3bf6b4a5,0xa6483b25,
0x36d7381d,0xb7323bce,0xbb3b3add,0xbb253303,0x395fbbea,0x3bb6b67c,0x39ed30b2,0xb4443b50,0xbb8833c6,0x2cb5ba8a,0x3564bbc3,0x3bfab89b,
0x2a483a6d,0xbbf139cb,0xbbfe38c4,0xafd6b984,0xbbd93aa7,0xba0f3179,0xb23eb872,0x393abbe2,0x323e3872,0xba4f3bff,0xbbd93aa7,0xb8eca648,
0x3bd9baa7,0x37323303,0x323e3872,0xbb253bce,0xb23eb872,0x3bb6bb50,0x3bd9baa7,0x3444367c,0x2a48b8c4,0x3a8abbf1,0x3bfeba6d,0x389bafd6,
0xbb3b381d,0xa648b732,0x36d7badd,0x3bffbb25,0xb9ed3bea,0xbac237e3,0xb95f30b2,0x3848baf6,0x356433c6,0xbb503bfa,0xbb883bc3,0xb67cacb5,
0x3ba8ba2f,0x35c2acb5,0xb4a53913,0xbb773bfa,0x3b0ebbf6,0x3a8ab8ec,0x378bae46,0xb89b3a4f,0x34a5b913,0x3bffbb99,0x3ba8ba2f,0xa6483505,
0xb78b2e46,0x3ac2bbb6,0x3b0ebbf6,0x3848b444,0xb81d395f,0xbbf13bff,0xbadd39ed,0xafd62648,0xb0b23564,0xbb993bce,0xbbea3b88,0xb5053303,
0x33c6aa48,0xbaf63b50,0xbbc33bfe,0xb7e3367c,0x38c4b6d7,0xba0f3a8a,0xba6d3b3b,0xb93a389b,0xb9a839a8,0x2fd6a648,0x39a8b9a8,0x3bf1bbff,
0xb9a839a8,0x3505b303,0x39a8b9a8,0x3b99bbce,0xb9a839a8,0x37e3b67c,0x39a8b9a8,0x3af6bb50,0xb9a839a8,0x393ab89b,0x39a8b9a8,0x3a0fba8a,
0x3addb9ed,0x3b77bbfa,0x381db95f,0xb5c22cb5,0x3beabb88,0x389bba4f,0x30b2b564,0xba8a38ec,0x3bc3bbfe,0x2648b505,0xb3c62a48,0xbbff3b99,
0x3a6dbb3b,0xb8483444,0xb8c436d7,0xbac23bb6,0x34a5b913,0xb89b2fd6,0xbba83a2f,0xba8a3bf1,0xb78b2e46,0xbbff3b25,0xbb0e3bf6,0x26483732,
0xbba83a2f,0xb8483af6,0xb4a53913,0x3ac2b7e3,0xbb0e3bf6,0x367c2cb5,0x378bae46,0x3b50bbfa,0xbbfe3a6d,0xb93a3be2,0xaa4838c4,0x3a0fb179,
0xb6d73add,0x38ec2648,0x3b3bb81d,0x3a4fbbff,0x395fb0b2,0x3b25bbce,0x39edbbea,0xb732b303,0x3b88bbc3,0xb444b67c,0xb564b3c6,0xbbb63b50,
0x323e3872,0x3b25b303,0x3bd9baa7,0x3732bbce,0x3bd9baa7,0x3444bb50,0xb23eb872,0xbbb6367c,0xb23eb872,0xbbfa389b,0xbbd93aa7,0xacb53a8a,
0xbbd93aa7,0x2fd63984,0x323e3872,0x3bf1b9cb,0x3b3bbadd,0x3303bbb6,0xb6d7b81d,0xbbce3444,0xb9edb0b2,0xbb773a0f,0xb95f3bea,0x35c2393a,
0xb5643bc3,0x3a8a2fd6,0x3b88b3c6,0x389bbbf1,0x3bfeb8c4,0x2648bb25,0xaa48ba6d,0xbbff3732,0xb913b78b,0xbbff3505,0xba2f3b0e,0x26483b99,
0xae463ba8,0x3ac23444,0x3bf6b4a5,0x3848bbb6,0x3a2fbb0e,0xb67cba0f,0xb913b78b,0xbb50393a,0xbbf634a5,0xb1793bf1,0xae463ba8,0x3be2afd6,
0xb8c43b3b,0x34443b77,0x3a6d36d7,0x3bb6b5c2,0x3addb95f,0xacb5bbe2,0xb81db9ed,0xbbfa3179,0xbbea3564,0xafd63bff,0x30b23b88,0x3bf12648,
0x3bc32a48,0x3505bbce,0x33c6bbfe,0xbb99b303,0x3b64361f,0x3af6b67c,0x361fbb64,0xb7e3bb50,0xbb64b61f,0xba0f389b,0xb61f3b64,0x393a3a8a,
0x3b64361f,0x38ecb9cb,0x361fbb64,0xba4fb984,0xbb64b61f,0xb7323ac2,0xb61f3b64,0x3b253848,0x30b2bb88,0xb984bb25,0xbbeab564,0xb9cb3732,
0x33c63bfe,0x3bce37e3,0x3bc3aa48,0x3303baf6,0xb8c4bb3b,0xbb772cb5,0xba6d36d7,0x35c23bfa,0x3add395f,0x389bb8ec,0x381db9ed,0xba8aba4f,
0xbbf6b4a5,0xb84837e3,0x2e463ba8,0x3ac23af6,0x3913b78b,0xb67cbbfa,0xba2fbb0e,0xbb50acb5,0x2e463ba8,0x3be238ec,0x3bf634a5,0x3179ba4f,
0xba2fbb0e,0xb9843505,0xb913378b,0x39cb3b99,0x35643bc3,0x3b993ac2,0x3b8833c6,0x3505b848,0xbbfeb8c4,0xb7e335c2,0xaa483a6d,0x3af63b77,
0x36d7b81d,0xba0fbbe2,0xbb3bbadd,0xb93a3179,0x395f3bea,0x3a4f2648,0x39edb0b2,0xb8ecbbff,0x3aa7323e,0x2cb5b89b,0xb872bbd9,0xbbfaba8a,
0x38723bd9,0x3bf13984,0x3aa7323e,0xafd6b9cb,0xbaa7b23e,0x35053ac2,0x38723bd9,0x3b993848,0xb872bbd9,0xbaf6b5c2,0xbaa7b23e,0x37e33b77,
0xb9edbbea,0xbbe2ba4f,0xb95fb0b2,0x317938ec,0x3564b3c6,0xb984bb99,0xbb88bbc3,0xb9cbb505,0x3bfe3a6d,0x3303b444,0xaa48b8c4,0xbbcebbb6,
0x36d73add,0x3b77393a,0x3b3b381d,0xb5c2ba0f,0xb78bae46,0x367c393a,0x3b0e3bf6,0x3b503a0f,0xbba8ba2f,0xb1792fd6,0x34a53913,0x3be23bf1,
0xbb0ebbf6,0xb984b732,0xb78bae46,0x39cb3b25,0xb4a5b913,0xbbcebaf6,0xbba8ba2f,0x330337e3,0x3bc33bfe,0x3a4f39cb,0x33c62a48,0xb8ecb984,
0x3a6d3b3b,0x3b253ac2,0x38c436d7,0xb732b848,0x381d395f,0x3bb63b77,0x3add39ed,0xb444b5c2,0x30b23564,0x3bfa3be2,0x3bea3b88,0xacb5b179,
0x3c003c00,0xb8ecb984,0,0x3a4f39cb,0x3c003c00,0xb732b848,0,0x3b253ac2,0x3c003c00,0xb444b5c2,0,0x3bb63b77,
0x3c003c00,0xacb5b179,0,0x3bfa3be2,0xb3c6aa48,0x3b503a0f,0xbbc3bbfe,0x367c393a,0xb8c4b6d7,0x3be23bf1,0xba6dbb3b,0xb1792fd6,
0xbaddb9ed,0x39cb3b25,0xb81db95f,0xb984b732,0xbbeabb88,0x330337e3,0xb0b2b564,0xbbcebaf6,0xbb0ebbf6,0x317938ec,0x378b2e46,0xbbe2ba4f,
0xb4a5b913,0xb9cbb505,0x3ba83a2f,0xb984bb99,0x378b2e46,0xbbcebbb6,0x3b0e3bf6,0x3303b444,0x3ba83a2f,0xb5c2ba0f,0x34a53913,0x3b77393a,
0x395f30b2,0xbbfaba8a,0x39ed3bea,0x2cb5b89b,0x3b883bc3,0xafd6b9cb,0xb56433c6,0x3bf13984,0x2a4838c4,0x3b993848,0xbbfeba6d,0x35053ac2,
0xbb3bb81d,0x37e33b77,0xb6d7badd,0xbaf6b5c2,0x38723bd9,0x3505b848,0xbaa7b23e,0x3b993ac2,0xbaa7b23e,0x3af63b77,0xb872bbd9,0xb7e335c2,
0xb872bbd9,0xb93a3179,0x3aa7323e,0xba0fbbe2,0x3aa7323e,0xb8ecbbff,0x38723bd9,0x3a4f2648,0xbb88b3c6,0x3ac23af6,0xb564bbc3,0xb84837e3,
0x2a48ba6d,0xbb50acb5,0x3bfe38c4,0xb67cbbfa,0x3b3b3add,0x3179ba4f,0xb6d7381d,0x3be238ec,0xb9ed30b2,0x39cb3b99,0xb95fbbea,0xb9843505,
0xae46bba8,0xb9cb3732,0x3bf634a5,0xb984bb25,0x3a2f3b0e,0x3303baf6,0xb913378b,0x3bce37e3,0xbbf6b4a5,0x35c23bfa,0xae46bba8,0xbb772cb5,
0x3913b78b,0xba8aba4f,0x3a2f3b0e,0x389bb8ec,0x3bea3564,0xb7e3bb50,0xb0b23b88,0x3af6b67c,0xbbc32a48,0x393a3a8a,0xb3c6bbfe,0xba0f389b,
0x3a6db6d7,0xba4fb984,0x38c43b3b,0x38ecb9cb,0xb81d39ed,0x3b253848,0xbaddb95f,0xb7323ac2,0xb61f3b64,0x3bb6b5c2,0xbb64b61f,0x34443b77,
0x361fbb64,0xbbfa3179,0x3b64361f,0xacb5bbe2,0xb61f3b64,0x3bf12648,0xbb64b61f,0xafd63bff,0x361fbb64,0xbb99b303,0x3b64361f,0x3505bbce,
0xba6db6d7,0x26483b99,0x38c4bb3b,0xbbff3505,0x381d39ed,0x3848bbb6,0xbadd395f,0x3ac23444,0xb0b2bb88,0xbb50393a,0x3beab564,0xb67cba0f,
0xb3c63bfe,0x3be2afd6,0xbbc3aa48,0xb1793bf1,0x3a2fbb0e,0xbbce3444,0x3913378b,0x3303bbb6,0xbbf634a5,0x35c2393a,0x2e46bba8,0xbb773a0f,
0x3913378b,0x389bbbf1,0xba2f3b0e,0x3a8a2fd6,0x2e46bba8,0xbbff3732,0x3bf6b4a5,0x2648bb25,0x36d7381d,0x3732bbce,0xbb3b3add,0x3b25b303,
0x395fbbea,0xbbb6367c,0x39ed30b2,0x3444bb50,0xbb8833c6,0xacb53a8a,0x3564bbc3,0xbbfa389b,0x2a483a6d,0x3bf1b9cb,0xbbfe38c4,0x2fd63984,
0xbbd93aa7,0x3a0fb179,0xb23eb872,0xb93a3be2,0x323e3872,0x3a4fbbff,0xbbd93aa7,0x38ec2648,0x3bd9baa7,0xb732b303,0x323e3872,0x3b25bbce,
0xb23eb872,0xbbb63b50,0x3bd9baa7,0xb444b67c,0x2a48b8c4,0xba8a3bf1,0x3bfeba6d,0xb89b2fd6,0xbb3b381d,0x26483732,0x36d7badd,0xbbff3b25,
0xb9ed3bea,0x3ac2b7e3,0xb95f30b2,0xb8483af6,0x356433c6,0x3b50bbfa,0xbb883bc3,0x367c2cb5,0x3ba8ba2f,0xb5c22cb5,0xb4a53913,0x3b77bbfa,
0x3b0ebbf6,0xba8a38ec,0x378bae46,0x389bba4f,0x34a5b913,0xbbff3b99,0x3ba8ba2f,0x2648b505,0xb78b2e46,0xbac23bb6,0x3b0ebbf6,0xb8483444,
0xb81d395f,0x3bf1bbff,0xbadd39ed,0x2fd6a648,0xb0b23564,0x3b99bbce,0xbbea3b88,0x3505b303,0x33c6aa48,0x3af6bb50,0xbbc33bfe,0x37e3b67c,
0x38c4b6d7,0x3a0fba8a,0xba6d3b3b,0x393ab89b,0xb9a839a8,0xafd62648,0x39a8b9a8,0xbbf13bff,0xb9a839a8,0xb5053303,0x39a8b9a8,0xbb993bce,
0xb9a839a8,0xb7e3367c,0x39a8b9a8,0xbaf63b50,0xb9a839a8,0xb93a389b,0x39a8b9a8,0xba0f3a8a,0x3addb9ed,0xbb773bfa,0x381db95f,0x35c2acb5,
0x3beabb88,0xb89b3a4f,0x30b2b564,0x3a8ab8ec,0x3bc3bbfe,0xa6483505,0xb3c62a48,0x3bffbb99,0x3a6dbb3b,0x3848b444,0xb8c436d7,0x3ac2bbb6,
0x34a5b913,0x389bafd6,0xbba83a2f,0x3a8abbf1,0xb78b2e46,0x3bffbb25,0xbb0e3bf6,0xa648b732,0xbba83a2f,0x3848baf6,0xb4a53913,0xbac237e3,
0xbb0e3bf6,0xb67cacb5,0x378bae46,0xbb503bfa,0xbbfe3a6d,0x393abbe2,0xaa4838c4,0xba0f3179,0xb6d73add,0xb8eca648,0x3b3bb81d,0xba4f3bff,
0x395fb0b2,0xbb253bce,0x39edbbea,0x37323303,0x3b88bbc3,0x3444367c,0xb564b3c6,0x3bb6bb50,0x323e3872,0xbb253303,0x3bd9baa7,0xb7323bce,
0x3bd9baa7,0xb4443b50,0xb23eb872,0x3bb6b67c,0xb23eb872,0x3bfab89b,0xbbd93aa7,0x2cb5ba8a,0xbbd93aa7,0xafd6b984,0x323e3872,0xbbf139cb,
0x3b3bbadd,0xb3033bb6,0xb6d7b81d,0x3bceb444,0xb9edb0b2,0x3b77ba0f,0xb95f3bea,0xb5c2b93a,0xb5643bc3,0xba8aafd6,0x3b88b3c6,0xb89b3bf1,
0x3bfeb8c4,0xa6483b25,0xaa48ba6d,0x3bffb732,0xb913b78b,0x3bffb505,0xba2f3b0e,0xa648bb99,0xae463ba8,0xbac2b444,0x3bf6b4a5,0xb8483bb6,
0x3a2fbb0e,0x367c3a0f,0xb913b78b,0x3b50b93a,0xbbf634a5,0x3179bbf1,0xae463ba8,0xbbe22fd6,0xb8c43b3b,0xb444bb77,0x3a6d36d7,0xbbb635c2,
0x3addb95f,0x2cb53be2,0xb81db9ed,0x3bfab179,0xbbea3564,0x2fd6bbff,0x30b23b88,0xbbf1a648,0x3bc32a48,0xb5053bce,0x33c6bbfe,0x3b993303,
0x3b64361f,0xbaf6367c,0x361fbb64,0x37e33b50,0xbb64b61f,0x3a0fb89b,0xb61f3b64,0xb93aba8a,0x3b64361f,0xb8ec39cb,0x361fbb64,0x3a4f3984,
0xbb64b61f,0x3732bac2,0xb61f3b64,0xbb25b848,0x30b2bb88,0x39843b25,0xbbeab564,0x39cbb732,0x33c63bfe,0xbbceb7e3,0x3bc3aa48,0xb3033af6,
0xb8c4bb3b,0x3b77acb5,0xba6d36d7,0xb5c2bbfa,0x3add395f,0xb89b38ec,0x381db9ed,0x3a8a3a4f,0xbbf6b4a5,0x3848b7e3,0x2e463ba8,0xbac2baf6,
0x3913b78b,0x367c3bfa,0xba2fbb0e,0x3b502cb5,0x2e463ba8,0xbbe2b8ec,0x3bf634a5,0xb1793a4f,0xba2fbb0e,0x3984b505,0xb913378b,0xb9cbbb99,
0x35643bc3,0xbb99bac2,0x3b8833c6,0xb5053848,0xbbfeb8c4,0x37e3b5c2,0xaa483a6d,0xbaf6bb77,0x36d7b81d,0x3a0f3be2,0xbb3bbadd,0x393ab179,
0x395f3bea,0xba4fa648,0x39edb0b2,0x38ec3bff,0x3aa7323e,0xacb5389b,0xb872bbd9,0x3bfa3a8a,0x38723bd9,0xbbf1b984,0x3aa7323e,0x2fd639cb,
0xbaa7b23e,0xb505bac2,0x38723bd9,0xbb99b848,0xb872bbd9,0x3af635c2,0xbaa7b23e,0xb7e3bb77,0xb9edbbea,0x3be23a4f,0xb95fb0b2,0xb179b8ec,
0x3564b3c6,0x39843b99,0xbb88bbc3,0x39cb3505,0x3bfe3a6d,0xb3033444,0xaa48b8c4,0x3bce3bb6,0x36d73add,0xbb77b93a,0x3b3b381d,0x35c23a0f,
0xb78bae46,0xb67cb93a,0x3b0e3bf6,0xbb50ba0f,0xbba8ba2f,0x3179afd6,0x34a53913,0xbbe2bbf1,0xbb0ebbf6,0x39843732,0xb78bae46,0xb9cbbb25,
0xb4a5b913,0x3bce3af6,0xbba8ba2f,0xb303b7e3,0x3bc33bfe,0xba4fb9cb,0x33c62a48,0x38ec3984,0x3a6d3b3b,0xbb25bac2,0x38c436d7,0x37323848,
0x381d395f,0xbbb6bb77,0x3add39ed,0x344435c2,0x30b23564,0xbbfabbe2,0x3bea3b88,0x2cb53179,0x3c003c00,0xafd6a648,0,0xbbf1bbff,
0x3c003c00,0xb505b303,0,0xbb99bbce,0x3c003c00,0xb7e3b67c,0,0xbaf6bb50,0x3c003c00,0xb93ab89b,0,0xba0fba8a,
0xbbc3bbfe,0x35c22cb5,0x33c62a48,0x3b773bfa,0xba6dbb3b,0x3a8a38ec,0x38c436d7,0x389b3a4f,0xb81db95f,0x3bff3b99,0x3add39ed,0x26483505,
0xb0b2b564,0x3ac23bb6,0x3bea3b88,0xb848b444,0x3b0e3bf6,0xb89bafd6,0xb78bae46,0xba8abbf1,0x34a53913,0xbbffbb25,0xbba8ba2f,0x2648b732,
0xb78bae46,0xb848baf6,0xbb0ebbf6,0x3ac237e3,0xbba8ba2f,0x367cacb5,0xb4a5b913,0x3b503bfa,0xb9edbbea,0x3a0f3179,0x395f30b2,0x393a3be2,
0x3564b3c6,0x3a4f3bff,0x3b883bc3,0xb8ec2648,0x3bfe3a6d,0xb7323303,0x2a4838c4,0xbb25bbce,0x36d73add,0xbbb6bb50,0xbb3bb81d,0x3444b67c,
0x38723bd9,0xbb25b303,0xbaa7b23e,0xb732bbce,0xbaa7b23e,0xb444bb50,0xb872bbd9,0x3bb6367c,0xb872bbd9,0x3bfa389b,0x3aa7323e,0x2cb53a8a,
0x3aa7323e,0xafd63984,0x38723bd9,0xbbf1b9cb,0xb564bbc3,0x3bce3444,0x3b8833c6,0x33033bb6,0x3bfe38c4,0xb5c2393a,0xaa483a6d,0xbb77ba0f,
0xb6d7381d,0xb89bbbf1,0xbb3bbadd,0x3a8aafd6,0xb95fbbea,0x3bff3732,0x39edb0b2,0x26483b25,0x2e463ba8,0xbbffb505,0xbbf6b4a5,0x2648bb99,
0xba2fbb0e,0x3ac2b444,0x3913b78b,0x38483bb6,0x3bf634a5,0xb67c3a0f,0x2e463ba8,0xbb50b93a,0xb913378b,0xb179bbf1,0xba2fbb0e,0x3be22fd6,
0x30b2bb88,0x3bb635c2,0x3bea3564,0xb4443b77,0x33c63bfe,0xbbfab179,0xbbc32a48,0x2cb5bbe2,0xb8c4bb3b,0x3bf1a648,0x3a6db6d7,0x2fd63bff,
0x3add395f,0xbb993303,0xb81d39ed,0xb505bbce,0xb61f3b64,0xbaf6b67c,0xbb64b61f,0x37e3bb50,0x361fbb64,0x3a0f389b,0x3b64361f,0xb93a3a8a,
0xb61f3b64,0xb8ecb9cb,0xbb64b61f,0x3a4fb984,0x361fbb64,0x37323ac2,0x3b64361f,0xbb253848,0x38c4bb3b,0x39cb3732,0x3a6d36d7,0xb9843b25,
0xbadd395f,0xb303baf6,0xb81db9ed,0x3bceb7e3,0x3beab564,0xb5c23bfa,0x30b23b88,0xbb77acb5,0xbbc3aa48,0x3a8aba4f,0x33c6bbfe,0x389b38ec,
0xba2f3b0e,0xb848b7e3,0xb913b78b,0x3ac2baf6,0x3bf6b4a5,0xb67c3bfa,0xae463ba8,0xbb502cb5,0xb913b78b,0x3be2b8ec,0x3a2fbb0e,0x31793a4f,
0xae463ba8,0xb984b505,0xbbf634a5,0x39cbbb99,0x3b3bbadd,0x35053848,0x36d7381d,0xbb993ac2,0xb9edb0b2,0x3af6bb77,0x395fbbea,0x37e335c2,
0xb5643bc3,0xb93ab179,0xbb8833c6,0x3a0fbbe2,0x3bfeb8c4,0xb8ec3bff,0x2a483a6d,0xba4f2648,0xbbd93aa7,0xacb5b89b,0xb23eb872,0x3bfaba8a,
0x323e3872,0xbbf13984,0xbbd93aa7,0x2fd6b9cb,0x3bd9baa7,0xb5053ac2,0x323e3872,0xbb993848,0xb23eb872,0x3af6b5c2,0x3bd9baa7,0xb7e33b77,
0x3bfeba6d,0xb17938ec,0xaa4838c4,0xbbe23a4f,0x36d7badd,0x39cbb505,0x3b3bb81d,0xb9843b99,0xb95f30b2,0x3bcebbb6,0x39edbbea,0x33033444,
0xbb883bc3,0x35c2ba0f,0xb564b3c6,0x3b77b93a,0xbba83a2f,0x367cb93a,0x34a5b913,0x3b50ba0f,0xbb0e3bf6,0xb179afd6,0xb78b2e46,0x3be2bbf1,
0xb4a53913,0xb9843732,0xbba83a2f,0x39cbbb25,0x378bae46,0xbbce3af6,0xbb0e3bf6,0x3303b7e3,0x3addb9ed,0xb8ec3984,0xb81d395f,0xba4f39cb,
0x3beabb88,0xb7323848,0xb0b23564,0xbb253ac2,0x3bc3bbfe,0xb44435c2,0x33c6aa48,0xbbb63b77,0x3a6dbb3b,0xacb53179,0x38c4b6d7,0xbbfa3be2,
0xb9a839a8,0x3a4fb9cb,0x39a8b9a8,0x38ecb984,0xb9a839a8,0x3b25bac2,0x39a8b9a8,0x3732b848,0xb9a839a8,0x3bb6bb77,0x39a8b9a8,0x3444b5c2,
0xb9a839a8,0x3bfabbe2,0x39a8b9a8,0x2cb5b179,0x381db95f,0xbb503a0f,0xbadd39ed,0xb67c393a,0x30b2b564,0xbbe23bf1,0xbbea3b88,0x31792fd6,
0xb3c62a48,0xb9cb3b25,0xbbc33bfe,0x3984b732,0xb8c436d7,0xb30337e3,0xba6d3b3b,0x3bcebaf6,0xb4a53913,0x3be2ba4f,0x3ba8ba2f,0x3179b8ec,
0x378bae46,0x3984bb99,0x3b0ebbf6,0xb9cb3505,0x3ba8ba2f,0xb303b444,0x34a5b913,0xbbce3bb6,0x3b0ebbf6,0xbb77393a,0xb78b2e46,0xb5c23a0f,
0x2a48b8c4,0xbbfa3a8a,0xbbfe3a6d,0x2cb5389b,0xbb3b381d,0xafd639cb,0xb6d73add,0x3bf1b984,0xb9ed3bea,0x3b99b848,0x395fb0b2,0x3505bac2,
0x356433c6,0x37e3bb77,0x3b88bbc3,0xbaf635c2,0x323e3872,0x3b99bac2,0x3bd9baa7,0xb505b848,0x3bd9baa7,0xb7e3b5c2,0xb23eb872,0xbaf63b77,
0xb23eb872,0xba0f3be2,0xbbd93aa7,0x393a3179,0xbbd93aa7,0x3a4fa648,0x323e3872,0x38ecbbff,0xb6d7b81d,0xbac23af6,0xbb3b3add,0x384837e3,
0xb95f3bea,0x3b50acb5,0x39ed30b2,0x367cbbfa,0x3b88b3c6,0xb179ba4f,0x3564bbc3,0xbbe238ec,0xaa48ba6d,0xb9cb3b99,0xbbfe38c4,0x39843505,
0x3913378b,0x3984bb25,0x3a2fbb0e,0xb9cbb732,0x2e46bba8,0xbbce37e3,0xbbf634a5,0x33033af6,0xba2f3b0e,0x3b772cb5,0x3913378b,0x35c2bbfa,
0x3bf6b4a5,0xb89bb8ec,0x2e46bba8,0xba8a3a4f,0xba6db6d7,0xb7e33b50,0xb8c43b3b,0x3af6367c,0x381d39ed,0x393aba8a,0x3addb95f,0xba0fb89b,
0xb0b2bb88,0xba4f3984,0xbbea3564,0x38ec39cb,0xb3c63bfe,0x3b25b848,0x3bc32a48,0xb732bac2,0x3b64361f,0x3444bb77,0x361fbb64,0xbbb6b5c2,
0xbb64b61f,0xacb53be2,0xb61f3b64,0x3bfa3179,0x3b64361f,0xafd6bbff,0x361fbb64,0xbbf12648,0xbb64b61f,0x35053bce,0xb61f3b64,0x3b99b303,
0xbbeab564,0xa6483b99,0xb0b23b88,0x3bff3505,0x3bc3aa48,0xb848bbb6,0xb3c6bbfe,0xbac23444,0xba6d36d7,0x3b50393a,0x38c43b3b,0x367cba0f,
0x381db9ed,0xbbe2afd6,0xbaddb95f,0x31793bf1,0x3bf634a5,0xb303bbb6,0xae46bba8,0xbbceb444,0xb913378b,0x3b773a0f,0x3a2f3b0e,0x35c2b93a,
0xae46bba8,0xba8a2fd6,0xbbf6b4a5,0x389b3bf1,0x3a2f3b0e,0xa648bb25,0x3913b78b,0xbbffb732,0xbb88b3c6,0x37323bce,0x35643bc3,0x3b253303,
0x2a48ba6d,0xbbb6b67c,0xbbfeb8c4,0x34443b50,0x3b3b3add,0xacb5ba8a,0x36d7b81d,0xbbfab89b,0xb9ed30b2,0x3bf139cb,0x395f3bea,0x2fd6b984,
0x3aa7323e,0xb93abbe2,0xb872bbd9,0xba0fb179,0x38723bd9,0x38eca648,0x3aa7323e,0xba4fbbff,0xbaa7b23e,0x3b253bce,0x38723bd9,0x3732b303,
0xb872bbd9,0xb444367c,0xbaa7b23e,0x3bb63b50,0xb95fb0b2,0x3a8a3bf1,0x39ed3bea,0x389b2fd6,0xbb88bbc3,0xa6483732,0xb56433c6,0x3bff3b25,
0xaa48b8c4,0xbac2b7e3,0xbbfeba6d,0x38483af6,0x3b3b381d,0xbb50bbfa,0xb6d7badd,0xb67c2cb5,0x378b2e46,0xbb77bbfa,0xbb0ebbf6,0xb5c2acb5,
0x3ba83a2f,0xb89bba4f,0xb4a5b913,0xba8ab8ec,0x3b0e3bf6,0xa648b505,0x378b2e46,0xbbffbb99,0x34a53913,0x38483444,0x3ba83a2f,0xbac2bbb6,
0xb3c6aa48,0x3bf13bff,0x3bc33bfe,0x2fd62648,0xb8c4b6d7,0x3b993bce,0x3a6d3b3b,0x35053303,0xbaddb9ed,0x3af63b50,0x381d395f,0x37e3367c,
0xbbeabb88,0x3a0f3a8a,0x30b23564,0x393a389b,0x3c003c00,0x2fd62648,0,0x3bf13bff,0x3c003c00,0x35053303,0,0x3b993bce,
0x3c003c00,0x37e3367c,0,0x3af63b50,0x3c003c00,0x393a389b,0,0x3a0f3a8a,0xbbc3bbfe,0xb5c2acb5,0x33c62a48,0xbb77bbfa,
0xba6dbb3b,0xba8ab8ec,0x38c436d7,0xb89bba4f,0xb81db95f,0xbbffbb99,0x3add39ed,0xa648b505,0xb0b2b564,0xbac2bbb6,0x3bea3b88,0x38483444,
0x3b0e3bf6,0x389b2fd6,0xb78bae46,0x3a8a3bf1,0x34a53913,0x3bff3b25,0xbba8ba2f,0xa6483732,0xb78bae46,0x38483af6,0xbb0ebbf6,0xbac2b7e3,
0xbba8ba2f,0xb67c2cb5,0xb4a5b913,0xbb50bbfa,0xb9edbbea,0xba0fb179,0x395f30b2,0xb93abbe2,0x3564b3c6,0xba4fbbff,0x3b883bc3,0x38eca648,
0x3bfe3a6d,0x3732b303,0x2a4838c4,0x3b253bce,0x36d73add,0x3bb63b50,0xbb3bb81d,0xb444367c,0x38723bd9,0x3b253303,0xbaa7b23e,0x37323bce,
0xbaa7b23e,0x34443b50,0xb872bbd9,0xbbb6b67c,0xb872bbd9,0xbbfab89b,0x3aa7323e,0xacb5ba8a,0x3aa7323e,0x2fd6b984,0x38723bd9,0x3bf139cb,
0xb564bbc3,0xbbceb444,0x3b8833c6,0xb303bbb6,0x3bfe38c4,0x35c2b93a,0xaa483a6d,0x3b773a0f,0xb6d7381d,0x389b3bf1,0xbb3bbadd,0xba8a2fd6,
0xb95fbbea,0xbbffb732,0x39edb0b2,0xa648bb25,0x2e463ba8,0x3bff3505,0xbbf6b4a5,0xa6483b99,0xba2fbb0e,0xbac23444,0x3913b78b,0xb848bbb6,
0x3bf634a5,0x367cba0f,0x2e463ba8,0x3b50393a,0xb913378b,0x31793bf1,0xba2fbb0e,0xbbe2afd6,0x30b2bb88,0xbbb6b5c2,0x3bea3564,0x3444bb77,
0x33c63bfe,0x3bfa3179,0xbbc32a48,0xacb53be2,0xb8c4bb3b,0xbbf12648,0x3a6db6d7,0xafd6bbff,0x3add395f,0x3b99b303,0xb81d39ed,0x35053bce,
0xb61f3b64,0x3af6367c,0xbb64b61f,0xb7e33b50,0x361fbb64,0xba0fb89b,0x3b64361f,0x393aba8a,0xb61f3b64,0x38ec39cb,0xbb64b61f,0xba4f3984,
0x361fbb64,0xb732bac2,0x3b64361f,0x3b25b848,0x38c4bb3b,0xb9cbb732,0x3a6d36d7,0x3984bb25,0xbadd395f,0x33033af6,0xb81db9ed,0xbbce37e3,
0x3beab564,0x35c2bbfa,0x30b23b88,0x3b772cb5,0xbbc3aa48,0xba8a3a4f,0x33c6bbfe,0xb89bb8ec,0xba2f3b0e,0x384837e3,0xb913b78b,0xbac23af6,
0x3bf6b4a5,0x367cbbfa,0xae463ba8,0x3b50acb5,0xb913b78b,0xbbe238ec,0x3a2fbb0e,0xb179ba4f,0xae463ba8,0x39843505,0xbbf634a5,0xb9cb3b99,
0x3b3bbadd,0xb505b848,0x36d7381d,0x3b99bac2,0xb9edb0b2,0xbaf63b77,0x395fbbea,0xb7e3b5c2,0xb5643bc3,0x393a3179,0xbb8833c6,0xba0f3be2,
0x3bfeb8c4,0x38ecbbff,0x2a483a6d,0x3a4fa648,0xbbd93aa7,0x2cb5389b,0xb23eb872,0xbbfa3a8a,0x323e3872,0x3bf1b984,0xbbd93aa7,0xafd639cb,
0x3bd9baa7,0x3505bac2,0x323e3872,0x3b99b848,0xb23eb872,0xbaf635c2,0x3bd9baa7,0x37e3bb77,0x3bfeba6d,0x3179b8ec,0xaa4838c4,0x3be2ba4f,
0x36d7badd,0xb9cb3505,0x3b3bb81d,0x3984bb99,0xb95f30b2,0xbbce3bb6,0x39edbbea,0xb303b444,0xbb883bc3,0xb5c23a0f,0xb564b3c6,0xbb77393a,
0xbba83a2f,0xb67c393a,0x34a5b913,0xbb503a0f,0xbb0e3bf6,0x31792fd6,0xb78b2e46,0xbbe23bf1,0xb4a53913,0x3984b732,0xbba83a2f,0xb9cb3b25,
0x378bae46,0x3bcebaf6,0xbb0e3bf6,0xb30337e3,0x3addb9ed,0x38ecb984,0xb81d395f,0x3a4fb9cb,0x3beabb88,0x3732b848,0xb0b23564,0x3b25bac2,
0x3bc3bbfe,0x3444b5c2,0x33c6aa48,0x3bb6bb77,0x3a6dbb3b,0x2cb5b179,0x38c4b6d7,0x3bfabbe2,0xb9a839a8,0xba4f39cb,0x39a8b9a8,0xb8ec3984,
0xb9a839a8,0xbb253ac2,0x39a8b9a8,0xb7323848,0xb9a839a8,0xbbb63b77,0x39a8b9a8,0xb44435c2,0xb9a839a8,0xbbfa3be2,0x39a8b9a8,0xacb53179,
0x381db95f,0x3b50ba0f,0xbadd39ed,0x367cb93a,0x30b2b564,0x3be2bbf1,0xbbea3b88,0xb179afd6,0xb3c62a48,0x39cbbb25,0xbbc33bfe,0xb9843732,
0xb8c436d7,0x3303b7e3,0xba6d3b3b,0xbbce3af6,0xb4a53913,0xbbe23a4f,0x3ba8ba2f,0xb17938ec,0x378bae46,0xb9843b99,0x3b0ebbf6,0x39cbb505,
0x3ba8ba2f,0x33033444,0x34a5b913,0x3bcebbb6,0x3b0ebbf6,0x3b77b93a,0xb78b2e46,0x35c2ba0f,0x2a48b8c4,0x3bfaba8a,0xbbfe3a6d,0xacb5b89b,
0xbb3b381d,0x2fd6b9cb,0xb6d73add,0xbbf13984,0xb9ed3bea,0xbb993848,0x395fb0b2,0xb5053ac2,0x356433c6,0xb7e33b77,0x3b88bbc3,0x3af6b5c2,
0x323e3872,0xbb993ac2,0x3bd9baa7,0x35053848,0x3bd9baa7,0x37e335c2,0xb23eb872,0x3af6bb77,0xb23eb872,0x3a0fbbe2,0xbbd93aa7,0xb93ab179,
0xbbd93aa7,0xba4f2648,0x323e3872,0xb8ec3bff,0xb6d7b81d,0x3ac2baf6,0xbb3b3add,0xb848b7e3,0xb95f3bea,0xbb502cb5,0x39ed30b2,0xb67c3bfa,
0x3b88b3c6,0x31793a4f,0x3564bbc3,0x3be2b8ec,0xaa48ba6d,0x39cbbb99,0xbbfe38c4,0xb984b505,0x3913378b,0xb9843b25,0x3a2fbb0e,0x39cb3732,
0x2e46bba8,0x3bceb7e3,0xbbf634a5,0xb303baf6,0xba2f3b0e,0xbb77acb5,0x3913378b,0xb5c23bfa,0x3bf6b4a5,0x389b38ec,0x2e46bba8,0x3a8aba4f,
0xba6db6d7,0x37e3bb50,0xb8c43b3b,0xbaf6b67c,0x381d39ed,0xb93a3a8a,0x3addb95f,0x3a0f389b,0xb0b2bb88,0x3a4fb984,0xbbea3564,0xb8ecb9cb,
0xb3c63bfe,0xbb253848,0x3bc32a48,0x37323ac2,0x3b64361f,0xb4443b77,0x361fbb64,0x3bb635c2,0xbb64b61f,0x2cb5bbe2,0xb61f3b64,0xbbfab179,
0x3b64361f,0x2fd63bff,0x361fbb64,0x3bf1a648,0xbb64b61f,0xb505bbce,0xb61f3b64,0xbb993303,0xbbeab564,0x2648bb99,0xb0b23b88,0xbbffb505,
0x3bc3aa48,0x38483bb6,0xb3c6bbfe,0x3ac2b444,0xba6d36d7,0xbb50b93a,0x38c43b3b,0xb67c3a0f,0x381db9ed,0x3be22fd6,0xbaddb95f,0xb179bbf1,
0x3bf634a5,0x33033bb6,0xae46bba8,0x3bce3444,0xb913378b,0xbb77ba0f,0x3a2f3b0e,0xb5c2393a,0xae46bba8,0x3a8aafd6,0xbbf6b4a5,0xb89bbbf1,
0x3a2f3b0e,0x26483b25,0x3913b78b,0x3bff3732,0xbb88b3c6,0xb732bbce,0x35643bc3,0xbb25b303,0x2a48ba6d,0x3bb6367c,0xbbfeb8c4,0xb444bb50,
0x3b3b3add,0x2cb53a8a,0x36d7b81d,0x3bfa389b,0xb9ed30b2,0xbbf1b9cb,0x395f3bea,0xafd63984,0x3aa7323e,0x393a3be2,0xb872bbd9,0x3a0f3179,
0x38723bd9,0xb8ec2648,0x3aa7323e,0x3a4f3bff,0xbaa7b23e,0xbb25bbce,0x38723bd9,0xb7323303,0xb872bbd9,0x3444b67c,0xbaa7b23e,0xbbb6bb50,
0xb95fb0b2,0xba8abbf1,0x39ed3bea,0xb89bafd6,0xbb88bbc3,0x2648b732,0xb56433c6,0xbbffbb25,0xaa48b8c4,0x3ac237e3,0xbbfeba6d,0xb848baf6,
0x3b3b381d,0x3b503bfa,0xb6d7badd,0x367cacb5,0x378b2e46,0x3b773bfa,0xbb0ebbf6,0x35c22cb5,0x3ba83a2f,0x389b3a4f,0xb4a5b913,0x3a8a38ec,
0x3b0e3bf6,0x26483505,0x378b2e46,0x3bff3b99,0x34a53913,0xb848b444,0x3ba83a2f,0x3ac23bb6,0xb3c6aa48,0xbbf1bbff,0x3bc33bfe,0xafd6a648,
0xb8c4b6d7,0xbb99bbce,0x3a6d3b3b,0xb505b303,0xbaddb9ed,0xbaf6bb50,0x381d395f,0xb7e3b67c,0xbbeabb88,0xba0fba8a,0x30b23564,0xb93ab89b,
0x3c003c00,0xba4fb9cb,0,0xb8ecb984,0x3c003c00,0xbb25bac2,0,0xb732b848,0x3c003c00,0xbbb6bb77,0,0xb444b5c2,
0x3c003c00,0xbbfabbe2,0,0xacb5b179,0x33c62a48,0x367c393a,0x3bc33bfe,0xbb50ba0f,0x38c436d7,0xb1792fd6,0x3a6d3b3b,0xbbe2bbf1,
0x3add39ed,0xb984b732,0x381d395f,0xb9cbbb25,0x3bea3b88,0xbbcebaf6,0x30b23564,0xb303b7e3,0xbb0ebbf6,0x3be23a4f,0x378b2e46,0x317938ec,
0xb4a5b913,0x39843b99,0x3ba83a2f,0xb9cbb505,0x378b2e46,0xb3033444,0x3b0e3bf6,0xbbcebbb6,0x3ba83a2f,0xbb77b93a,0x34a53913,0xb5c2ba0f,
0xb95fb0b2,0x2cb5b89b,0xb9edbbea,0x3bfa3a8a,0xbb88bbc3,0x3bf13984,0x3564b3c6,0x2fd639cb,0xaa48b8c4,0x35053ac2,0x3bfe3a6d,0xbb99b848,
0x3b3b381d,0xbaf6b5c2,0x36d73add,0xb7e3bb77,0x38723bd9,0xbb99bac2,0xbaa7b23e,0x3505b848,0xbaa7b23e,0x37e3b5c2,0xb872bbd9,0x3af63b77,
0xb872bbd9,0x3a0f3be2,0x3aa7323e,0xb93a3179,0x3aa7323e,0xba4fa648,0x38723bd9,0xb8ecbbff,0x3b8833c6,0xb84837e3,0x35643bc3,0xbac2baf6,
0xaa483a6d,0xb67cbbfa,0xbbfeb8c4,0x3b502cb5,0xbb3bbadd,0x3be238ec,0x36d7b81d,0xb1793a4f,0x39edb0b2,0xb9843505,0x395f3bea,0xb9cbbb99,
0xae46bba8,0x39843b25,0x3bf634a5,0xb9cb3732,0x3a2f3b0e,0xbbceb7e3,0xb913378b,0x3303baf6,0xbbf6b4a5,0x3b77acb5,0xae46bba8,0x35c23bfa,
0x3913b78b,0xb89b38ec,0x3a2f3b0e,0xba8aba4f,0xbbeab564,0x3af6b67c,0x30b2bb88,0x37e33b50,0x3bc3aa48,0xba0f389b,0x33c63bfe,0xb93aba8a,
0xba6d36d7,0x38ecb9cb,0xb8c4bb3b,0x3a4f3984,0x381db9ed,0xb7323ac2,0x3add395f,0xbb25b848,0xb61f3b64,0xb444bb77,0xbb64b61f,0x3bb6b5c2,
0x361fbb64,0x2cb53be2,0x3b64361f,0xbbfa3179,0xb61f3b64,0x2fd6bbff,0xbb64b61f,0x3bf12648,0x361fbb64,0xb5053bce,0x3b64361f,0xbb99b303,
0x3a6d36d7,0xbbff3505,0xb8c43b3b,0xa648bb99,0xb81db9ed,0x3ac23444,0x3addb95f,0xb8483bb6,0x30b23b88,0xb67cba0f,0xbbea3564,0x3b50b93a,
0x33c6bbfe,0xb1793bf1,0x3bc32a48,0xbbe22fd6,0x3a2fbb0e,0xb3033bb6,0x3913378b,0xbbce3444,0xbbf634a5,0x3b77ba0f,0x2e46bba8,0x35c2393a,
0x3913378b,0xba8aafd6,0xba2f3b0e,0x389bbbf1,0x2e46bba8,0xa6483b25,0x3bf6b4a5,0xbbff3732,0xb6d7b81d,0x3b25b303,0x3b3bbadd,0xb7323bce,
0xb95f3bea,0x3444bb50,0xb9edb0b2,0x3bb6b67c,0x3b88b3c6,0xbbfa389b,0xb5643bc3,0x2cb5ba8a,0xaa48ba6d,0x2fd63984,0x3bfeb8c4,0xbbf139cb,
0xbbd93aa7,0x393abbe2,0xb23eb872,0x3a0fb179,0x323e3872,0xb8eca648,0xbbd93aa7,0x3a4fbbff,0x3bd9baa7,0xbb253bce,0x323e3872,0xb732b303,
0xb23eb872,0x3444367c,0x3bd9baa7,0xbbb63b50,0xaa4838c4,0xb89b2fd6,0xbbfe3a6d,0x3a8abbf1,0x3b3bb81d,0xbbff3b25,0xb6d73add,0xa648b732,
0x39edbbea,0xb8483af6,0x395fb0b2,0xbac237e3,0xb564b3c6,0x367c2cb5,0x3b88bbc3,0xbb503bfa,0x3ba8ba2f,0xbb773bfa,0xb4a53913,0xb5c22cb5,
0x3b0ebbf6,0xb89b3a4f,0x378bae46,0xba8a38ec,0x34a5b913,0xa6483505,0x3ba8ba2f,0xbbff3b99,0xb78b2e46,0x3848b444,0x3b0ebbf6,0xbac23bb6,
0x381db95f,0x2fd6a648,0x3addb9ed,0xbbf13bff,0x30b2b564,0x3505b303,0x3beabb88,0xbb993bce,0xb3c62a48,0x37e3b67c,0x3bc3bbfe,0xbaf63b50,
0xb8c436d7,0x393ab89b,0x3a6dbb3b,0xba0f3a8a,0xb9a839a8,0x3bf1bbff,0x39a8b9a8,0xafd62648,0xb9a839a8,0x3b99bbce,0x39a8b9a8,0xb5053303,
0xb9a839a8,0x3af6bb50,0x39a8b9a8,0xb7e3367c,0xb9a839a8,0x3a0fba8a,0x39a8b9a8,0xb93a389b,0xbadd39ed,0x35c2acb5,0xb81d395f,0x3b77bbfa,
0xbbea3b88,0x3a8ab8ec,0xb0b23564,0x389bba4f,0xbbc33bfe,0x3bffbb99,0x33c6aa48,0x2648b505,0xba6d3b3b,0x3ac2bbb6,0x38c4b6d7,0xb8483444,
0x34a5b913,0xba8a3bf1,0xbba83a2f,0x389bafd6,0xb78b2e46,0x26483732,0xbb0e3bf6,0x3bffbb25,0xbba83a2f,0x3ac2b7e3,0xb4a53913,0x3848baf6,
0xbb0e3bf6,0x3b50bbfa,0x378bae46,0xb67cacb5,0x3bfeba6d,0xba0f3179,0x2a48b8c4,0xb93a3be2,0x36d7badd,0xba4f3bff,0xbb3b381d,0x38ec2648,
0xb95f30b2,0x37323303,0xb9ed3bea,0x3b25bbce,0xbb883bc3,0x3bb6bb50,0x356433c6,0xb444b67c,0x323e3872,0x3732bbce,0x3bd9baa7,0xbb253303,
0x3bd9baa7,0xbbb6367c,0xb23eb872,0xb4443b50,0xb23eb872,0xacb53a8a,0xbbd93aa7,0x3bfab89b,0xbbd93aa7,0x3bf1b9cb,0x323e3872,0xafd6b984,
0xbb3b3add,0x3bceb444,0x36d7381d,0x3303bbb6,0x39ed30b2,0xb5c2b93a,0x395fbbea,0xbb773a0f,0x3564bbc3,0xb89b3bf1,0xbb8833c6,0x3a8a2fd6,
0xbbfe38c4,0x3bffb732,0x2a483a6d,0x2648bb25,0xb913b78b,0x26483b99,0xba2f3b0e,0x3bffb505,0xae463ba8,0x3848bbb6,0x3bf6b4a5,0xbac2b444,
0x3a2fbb0e,0xbb50393a,0xb913b78b,0x367c3a0f,0xbbf634a5,0x3be2afd6,0xae463ba8,0x3179bbf1,0x38c4bb3b,0xbbb635c2,0xba6db6d7,0x34443b77,
0xbadd395f,0x3bfab179,0x381d39ed,0xacb5bbe2,0x3beab564,0xbbf1a648,0xb0b2bb88,0xafd63bff,0xbbc3aa48,0x3b993303,0xb3c63bfe,0x3505bbce,
0x3b64361f,0xb7e3bb50,0x361fbb64,0xbaf6367c,0xbb64b61f,0x393a3a8a,0xb61f3b64,0x3a0fb89b,0x3b64361f,0xba4fb984,0x361fbb64,0xb8ec39cb,
0xbb64b61f,0x3b253848,0xb61f3b64,0x3732bac2,0xb0b23b88,0x39cbb732,0x3bea3564,0xb984bb25,0xb3c6bbfe,0xb3033af6,0xbbc32a48,0x3bce37e3,
0x38c43b3b,0xb5c2bbfa,0x3a6db6d7,0xbb772cb5,0xbaddb95f,0x3a8a3a4f,0xb81d39ed,0x389bb8ec,0xbbf6b4a5,0x3ac23af6,0x2e463ba8,0x3848b7e3,
0x3913b78b,0xbb50acb5,0xba2fbb0e,0x367c3bfa,0x2e463ba8,0x3179ba4f,0x3bf634a5,0xbbe2b8ec,0xba2fbb0e,0x39cb3b99,0xb913378b,0x3984b505,
0xb564bbc3,0xb5053848,0xbb88b3c6,0x3b993ac2,0x3bfe38c4,0xbaf6bb77,0x2a48ba6d,0xb7e335c2,0xb6d7381d,0x393ab179,0x3b3b3add,0xba0fbbe2,
0xb95fbbea,0x38ec3bff,0xb9ed30b2,0x3a4f2648,0x3aa7323e,0xbbfaba8a,0xb872bbd9,0xacb5389b,0x38723bd9,0xafd6b9cb,0x3aa7323e,0xbbf1b984,
0xbaa7b23e,0x3b993848,0x38723bd9,0xb505bac2,0xb872bbd9,0x37e33b77,0xbaa7b23e,0x3af635c2,0x39ed3bea,0xb179b8ec,0x395f30b2,0xbbe2ba4f,
0xb56433c6,0x39cb3505,0x3b883bc3,0xb984bb99,0xbbfeba6d,0x3bce3bb6,0x2a4838c4,0x3303b444,0xb6d7badd,0x35c23a0f,0xbb3bb81d,0x3b77393a,
0xb78bae46,0x3b503a0f,0x3b0e3bf6,0xb67cb93a,0xbba8ba2f,0x3be23bf1,0x34a53913,0x3179afd6,0xbb0ebbf6,0x39cb3b25,0xb78bae46,0x39843732,
0xb4a5b913,0x330337e3,0xbba8ba2f,0x3bce3af6,0xbbc3bbfe,0x38ec3984,0xb3c6aa48,0x3a4f39cb,0xba6dbb3b,0x37323848,0xb8c4b6d7,0x3b253ac2,
0xb81db95f,0x344435c2,0xbaddb9ed,0x3bb63b77,0xb0b2b564,0x2cb53179,0xbbeabb88,0x3bfa3be2,0x3c003c00,0x3a4f39cb,0,0x38ec3984,
0x3c003c00,0x3b253ac2,0,0x37323848,0x3c003c00,0x3bb63b77,0,0x344435c2,0x3c003c00,0x3bfa3be2,0,0x2cb53179,
0x33c62a48,0xb67cb93a,0x3bc33bfe,0x3b503a0f,0x38c436d7,0x3179afd6,0x3a6d3b3b,0x3be23bf1,0x3add39ed,0x39843732,0x381d395f,0x39cb3b25,
0x3bea3b88,0x3bce3af6,0x30b23564,0x330337e3,0xbb0ebbf6,0xbbe2ba4f,0x378b2e46,0xb179b8ec,0xb4a5b913,0xb984bb99,0x3ba83a2f,0x39cb3505,
0x378b2e46,0x3303b444,0x3b0e3bf6,0x3bce3bb6,0x3ba83a2f,0x3b77393a,0x34a53913,0x35c23a0f,0xb95fb0b2,0xacb5389b,0xb9edbbea,0xbbfaba8a,
0xbb88bbc3,0xbbf1b984,0x3564b3c6,0xafd6b9cb,0xaa48b8c4,0xb505bac2,0x3bfe3a6d,0x3b993848,0x3b3b381d,0x3af635c2,0x36d73add,0x37e33b77,
0x38723bd9,0x3b993ac2,0xbaa7b23e,0xb5053848,0xbaa7b23e,0xb7e335c2,0xb872bbd9,0xbaf6bb77,0xb872bbd9,0xba0fbbe2,0x3aa7323e,0x393ab179,
0x3aa7323e,0x3a4f2648,0x38723bd9,0x38ec3bff,0x3b8833c6,0x3848b7e3,0x35643bc3,0x3ac23af6,0xaa483a6d,0x367c3bfa,0xbbfeb8c4,0xbb50acb5,
0xbb3bbadd,0xbbe2b8ec,0x36d7b81d,0x3179ba4f,0x39edb0b2,0x3984b505,0x395f3bea,0x39cb3b99,0xae46bba8,0xb984bb25,0x3bf634a5,0x39cbb732,
0x3a2f3b0e,0x3bce37e3,0xb913378b,0xb3033af6,0xbbf6b4a5,0xbb772cb5,0xae46bba8,0xb5c2bbfa,0x3913b78b,0x389bb8ec,0x3a2f3b0e,0x3a8a3a4f,
0xbbeab564,0xbaf6367c,0x30b2bb88,0xb7e3bb50,0x3bc3aa48,0x3a0fb89b,0x33c63bfe,0x393a3a8a,0xba6d36d7,0xb8ec39cb,0xb8c4bb3b,0xba4fb984,
0x381db9ed,0x3732bac2,0x3add395f,0x3b253848,0xb61f3b64,0x34443b77,0xbb64b61f,0xbbb635c2,0x361fbb64,0xacb5bbe2,0x3b64361f,0x3bfab179,
0xb61f3b64,0xafd63bff,0xbb64b61f,0xbbf1a648,0x361fbb64,0x3505bbce,0x3b64361f,0x3b993303,0x3a6d36d7,0x3bffb505,0xb8c43b3b,0x26483b99,
0xb81db9ed,0xbac2b444,0x3addb95f,0x3848bbb6,0x30b23b88,0x367c3a0f,0xbbea3564,0xbb50393a,0x33c6bbfe,0x3179bbf1,0x3bc32a48,0x3be2afd6,
0x3a2fbb0e,0x3303bbb6,0x3913378b,0x3bceb444,0xbbf634a5,0xbb773a0f,0x2e46bba8,0xb5c2b93a,0x3913378b,0x3a8a2fd6,0xba2f3b0e,0xb89b3bf1,
0x2e46bba8,0x2648bb25,0x3bf6b4a5,0x3bffb732,0xb6d7b81d,0xbb253303,0x3b3bbadd,0x3732bbce,0xb95f3bea,0xb4443b50,0xb9edb0b2,0xbbb6367c,
0x3b88b3c6,0x3bfab89b,0xb5643bc3,0xacb53a8a,0xaa48ba6d,0xafd6b984,0x3bfeb8c4,0x3bf1b9cb,0xbbd93aa7,0xb93a3be2,0xb23eb872,0xba0f3179,
0x323e3872,0x38ec2648,0xbbd93aa7,0xba4f3bff,0x3bd9baa7,0x3b25bbce,0x323e3872,0x37323303,0xb23eb872,0xb444b67c,0x3bd9baa7,0x3bb6bb50,
0xaa4838c4,0x389bafd6,0xbbfe3a6d,0xba8a3bf1,0x3b3bb81d,0x3bffbb25,0xb6d73add,0x26483732,0x39edbbea,0x3848baf6,0x395fb0b2,0x3ac2b7e3,
0xb564b3c6,0xb67cacb5,0x3b88bbc3,0x3b50bbfa,0x3ba8ba2f,0x3b77bbfa,0xb4a53913,0x35c2acb5,0x3b0ebbf6,0x389bba4f,0x378bae46,0x3a8ab8ec,
0x34a5b913,0x2648b505,0x3ba8ba2f,0x3bffbb99,0xb78b2e46,0xb8483444,0x3b0ebbf6,0x3ac2bbb6,0x381db95f,0xafd62648,0x3addb9ed,0x3bf1bbff,
0x30b2b564,0xb5053303,0x3beabb88,0x3b99bbce,0xb3c62a48,0xb7e3367c,0x3bc3bbfe,0x3af6bb50,0xb8c436d7,0xb93a389b,0x3a6dbb3b,0x3a0fba8a,
0xb9a839a8,0xbbf13bff,0x39a8b9a8,0x2fd6a648,0xb9a839a8,0xbb993bce,0x39a8b9a8,0x3505b303,0xb9a839a8,0xbaf63b50,0x39a8b9a8,0x37e3b67c,
0xb9a839a8,0xba0f3a8a,0x39a8b9a8,0x393ab89b,0xbadd39ed,0xb5c22cb5,0xb81d395f,0xbb773bfa,0xbbea3b88,0xba8a38ec,0xb0b23564,0xb89b3a4f,
0xbbc33bfe,0xbbff3b99,0x33c6aa48,0xa6483505,0xba6d3b3b,0xbac23bb6,0x38c4b6d7,0x3848b444,0x34a5b913,0x3a8abbf1,0xbba83a2f,0xb89b2fd6,
0xb78b2e46,0xa648b732,0xbb0e3bf6,0xbbff3b25,0xbba83a2f,0xbac237e3,0xb4a53913,0xb8483af6,0xbb0e3bf6,0xbb503bfa,0x378bae46,0x367c2cb5,
0x3bfeba6d,0x3a0fb179,0x2a48b8c4,0x393abbe2,0x36d7badd,0x3a4fbbff,0xbb3b381d,0xb8eca648,0xb95f30b2,0xb732b303,0xb9ed3bea,0xbb253bce,
0xbb883bc3,0xbbb63b50,0x356433c6,0x3444367c,0x323e3872,0xb7323bce,0x3bd9baa7,0x3b25b303,0x3bd9baa7,0x3bb6b67c,0xb23eb872,0x3444bb50,
0xb23eb872,0x2cb5ba8a,0xbbd93aa7,0xbbfa389b,0xbbd93aa7,0xbbf139cb,0x323e3872,0x2fd63984,0xbb3b3add,0xbbce3444,0x36d7381d,0xb3033bb6,
0x39ed30b2,0x35c2393a,0x395fbbea,0x3b77ba0f,0x3564bbc3,0x389bbbf1,0xbb8833c6,0xba8aafd6,0xbbfe38c4,0xbbff3732,0x2a483a6d,0xa6483b25,
0xb913b78b,0xa648bb99,0xba2f3b0e,0xbbff3505,0xae463ba8,0xb8483bb6,0x3bf6b4a5,0x3ac23444,0x3a2fbb0e,0x3b50b93a,0xb913b78b,0xb67cba0f,
0xbbf634a5,0xbbe22fd6,0xae463ba8,0xb1793bf1,0x38c4bb3b,0x3bb6b5c2,0xba6db6d7,0xb444bb77,0xbadd395f,0xbbfa3179,0x381d39ed,0x2cb53be2,
0x3beab564,0x3bf12648,0xb0b2bb88,0x2fd6bbff,0xbbc3aa48,0xbb99b303,0xb3c63bfe,0xb5053bce,0x3b64361f,0x37e33b50,0x361fbb64,0x3af6b67c,
0xbb64b61f,0xb93aba8a,0xb61f3b64,0xba0f389b,0x3b64361f,0x3a4f3984,0x361fbb64,0x38ecb9cb,0xbb64b61f,0xbb25b848,0xb61f3b64,0xb7323ac2,
0xb0b23b88,0xb9cb3732,0x3bea3564,0x39843b25,0xb3c6bbfe,0x3303baf6,0xbbc32a48,0xbbceb7e3,0x38c43b3b,0x35c23bfa,0x3a6db6d7,0x3b77acb5,
0xbaddb95f,0xba8aba4f,0xb81d39ed,0xb89b38ec,0xbbf6b4a5,0xbac2baf6,0x2e463ba8,0xb84837e3,0x3913b78b,0x3b502cb5,0xba2fbb0e,0xb67cbbfa,
0x2e463ba8,0xb1793a4f,0x3bf634a5,0x3be238ec,0xba2fbb0e,0xb9cbbb99,0xb913378b,0xb9843505,0xb564bbc3,0x3505b848,0xbb88b3c6,0xbb99bac2,
0x3bfe38c4,0x3af63b77,0x2a48ba6d,0x37e3b5c2,0xb6d7381d,0xb93a3179,0x3b3b3add,0x3a0f3be2,0xb95fbbea,0xb8ecbbff,0xb9ed30b2,0xba4fa648,
0x3aa7323e,0x3bfa3a8a,0xb872bbd9,0x2cb5b89b,0x38723bd9,0x2fd639cb,0x3aa7323e,0x3bf13984,0xbaa7b23e,0xbb99b848,0x38723bd9,0x35053ac2,
0xb872bbd9,0xb7e3bb77,0xbaa7b23e,0xbaf6b5c2,0x39ed3bea,0x317938ec,0x395f30b2,0x3be23a4f,0xb56433c6,0xb9cbb505,0x3b883bc3,0x39843b99,
0xbbfeba6d,0xbbcebbb6,0x2a4838c4,0xb3033444,0xb6d7badd,0xb5c2ba0f,0xbb3bb81d,0xbb77b93a,0xb78bae46,0xbb50ba0f,0x3b0e3bf6,0x367c393a,
0xbba8ba2f,0xbbe2bbf1,0x34a53913,0xb1792fd6,0xbb0ebbf6,0xb9cbbb25,0xb78bae46,0xb984b732,0xb4a5b913,0xb303b7e3,0xbba8ba2f,0xbbcebaf6,
0xbbc3bbfe,0xb8ecb984,0xb3c6aa48,0xba4fb9cb,0xba6dbb3b,0xb732b848,0xb8c4b6d7,0xbb25bac2,0xb81db95f,0xb444b5c2,0xbaddb9ed,0xbbb6bb77,
0xb0b2b564,0xacb5b179,0xbbeabb88,0xbbfabbe2,0x3c003c00,0x96480000,0x3c003c00,0xa311a248,0x3c003c00,0x9cb69a48,0x3c003c00,0xa452a3db,
0x3c003c00,0x9fdb9e48,0x3c003c00,0xa51ba4b6,0x3c003c00,0xa17fa0b6,0x3bff3c00,0xa5e4a57f,0x3c003c00,0x9fdb0000,0x3bfb3bfc,0xac6aabd9,
0x3bff3c00,0xa5e4a3db,0x3bf93bfa,0xad65ace7,0x3bfe3bff,0xa8e8a7da,0x3bf63bf7,0xae5fade2,0x3bfd3bfe,0xaadea9e3,0x3bf23bf4,0xaf59aedc,
0x3c003c00,0xa3110000,0x3bf03bf4,0xafefaf0e,0x3bfe3bff,0xa94da711,0x3be83bed,0xb0d7b067,0x3bfb3bfd,0xac6aab11,0x3bdf3be4,0xb1b6b147,
0x3bf63bf9,0xae2dad4c,0x3bd43bda,0xb294b226,0x3c003c00,0xa51b0000,0x3bdf3be6,0xb1b6b115,0x3bfc3bfe,0xaba7a91b,0x3bcf3bd7,0xb2f7b257,
0x3bf63bf9,0xae5fad1a,0x3bbc3bc6,0xb41ab396,0x3bec3bf1,0xb074afa4,0x3ba53bb1,0xb4b7b469,0x3bff3c00,0xa6ad0000,0x3bc83bd4,0xb371b2a1,
0x3bfa3bfd,0xad00aaac,0x3bac3bbb,0xb487b420,0x3bef3bf5,0xb029aeaa,0x3b8b3b9d,0xb552b4ed,0x3bde3be7,0xb1cfb0fd,0x3b653b79,0xb61ab5b6,
0x3bff3c00,0xa81f0000,0x3bab3bbc,0xb493b414,0x3bf63bfc,0xae2dac1f,0x3b813b97,0xb58db511,0x3be53bef,0xb122b01d,0x3b4f3b69,0xb682b608,
0x3bcc3bda,0xb328b226,0x3b163b33,0xb76fb6f9,0x3bfe3c00,0xa8e80000,0x3b873ba0,0xb56ab4d5,0x3bf23bfa,0xaf59ace7,0x3b4c3b6b,0xb68db5fd,
0x3bda3be8,0xb219b0e4,0x3b073b2b,0xb7a6b71b,0x3bb73bca,0xb43eb34c,0x3ab63ae0,0xb85ab817,0x3bfe3c00,0xa9b10000,0x3b5e3b80,0xb63cb593,
0x3bee3bf8,0xb042adb0,0x3b103b39,0xb785b6e3,0x3bce3be0,0xb30fb1aa,0x3ab33ae3,0xb85fb812,0x3b9e3bb7,0xb4e7b438,0x3a493a7f,0xb8f3b8ab,
0x3bfd3c00,0xaa7a0000,0x3b2f3b5a,0xb70ab64e,0x3be83bf6,0xb0d7ae78,0x3acb3aff,0xb83ab7c2,0x3bbf3bd6,0xb402b26f,0x3a543a92,0xb8e5b891,
0x3b813ba2,0xb58db4c9,0x39cd3a13,0xb982b935,0x3bfd3c00,0xab430000,0x3afb3b30,0xb7d2b705,0x3be23bf3,0xb16caf40,0x3a7e3abf,0xb8adb84d,
0x3bae3bcb,0xb47bb334,0x39eb3a37,0xb962b909,0x3b603b8a,0xb631b558,0x3946399b,0xba04b9b5,0x3bfc3c00,0xac060000,0x3ac13b02,0xb84ab7b7,
0x3bdc3bf0,0xb201b004,0x3a293a78,0xb91bb8b5,0x3b9c3bc0,0xb4f3b3f7,0x397939d4,0xb9d6b97b,0x3b3d3b70,0xb6d2b5e5,0x38b23918,0xba7aba2b,
0x3bfb3c00,0xac6a0000,0x3a813ad0,0xb8a8b832,0x3bd43bed,0xb294b067,0x39cd3a2b,0xb982b918,0x3b873bb2,0xb56ab45d,0x38fd3969,0xba41b9e5,
0x3b163b53,0xb76fb670,0x3815388c,0xbae1ba95,0x3bfa3c00,0xacce0000,0x3a3d3a99,0xb902b887,0x3bcc3be9,0xb328b0cb,0x396b39d8,0xb9e3b976,
0x3b713ba4,0xb5dfb4bd,0x387a38f6,0xbaa2ba47,0x3aeb3b33,0xb805b6f9,0x36dd37ee,0xbb3abaf3,0x3bf93c00,0xad330000,0x39f43a5e,0xb958b8d8,
0x3bc33be5,0xb3bab12e,0x39023980,0xba3db9d0,0x3b593b95,0xb654b51d,0x37dd387c,0xbaf7baa0,0x3abd3b11,0xb850b780,0x358136b5,0xbb83bb43,
0x3bf83c00,0xad970000,0x39a63a1f,0xb9aab927,0x3bba3be1,0xb426b191,0x38943922,0xba90ba23,0x3b3f3b84,0xb6c6b57c,0x36bb37f9,0xbb42baf0,
0x3a8c3aed,0xb899b802,0x341a3570,0xbbbcbb86,0x3bf73c00,0xadfb0000,0x395439dc,0xb9f8b972,0x3bb03bdc,0xb46fb1f4,0x382038bf,0xbadbba71,
0x3b243b72,0xb737b5da,0x358d36ee,0xbb81bb36,0x3a583ac6,0xb8e0b842,0x31533420,0xbbe3bbbb,0x3bf63c00,0xae5f0000,0x38fd3996,0xba41b9ba,
0x3ba53bd7,0xb4b7b257,0x374e3858,0xbb1ebab8,0x3b073b5f,0xb7a6b637,0x345735da,0xbbb3bb72,0x3a213a9c,0xb924b881,0x2cce3191,0xbbfabbe1,
0x3bf53c00,0xaec30000,0x38a3394d,0xba85b9fe,0x3b9a3bd2,0xb4ffb2b9,0x365437d8,0xbb59baf9,0x3ae83b4b,0xb80ab693,0x323234bd,0xbbd9bba4,
0x39e73a71,0xb966b8bf,0xa4522db0,0xbc00bbf8,0x3bf33c00,0xaf270000,0x38453900,0xbac4ba3f,0x3b8e3bcd,0xb546b31b,0x355236f9,0xbb8bbb33,
0x3ac73b36,0xb840b6ee,0x2f593334,0xbbf2bbcb,0x39aa3a43,0xb9a6b8fb,0xaef51a48,0xbbf4bc00,0x3bf23c00,0xaf8b0000,0x37c838b0,0xbafeba7c,
0x3b813bc7,0xb58db37d,0x344b3614,0xbbb5bb67,0x3aa53b20,0xb874b748,0x288430e4,0xbbffbbe8,0x396b3a13,0xb9e3b935,0xb263ad4c,0xbbd7bbf9,
0x3bf03c00,0xafef0000,0x36ff385d,0xbb32bab5,0x3b733bc1,0xb5d4b3df,0x327c3529,0xbbd6bb93,0x3a813b08,0xb8a8b7a1,0xa9b12d1a,0xbbfebbf9,
0x392939e1,0xba1db96d,0xb49fb160,0xbba9bbe3,0x3bef3c00,0xb0290000,0x36313807,0xbb60bae9,0x3b653bbb,0xb61ab420,0x305b3438,0xbbedbbb7,
0x3a5c3af0,0xb8dbb7f9,0xafef1e48,0xbbf0bc00,0x38e539ad,0xba54b9a4,0xb602b408,0xbb6abbbe,0x3bed3c00,0xb05b0000,0x355e375e,0xbb89bb1a,
0x3b573bb4,0xb65fb451,0x2c6a3288,0xbbfbbbd5,0x3a353ad6,0xb90cb828,0xb27cac51,0xbbd6bbfb,0x389e3976,0xba89b9d8,0xb759b558,0xbb1bbb8a,
0x3beb3c00,0xb08d0000,0x348736aa,0xbbacbb46,0x3b473bad,0xb6a4b481,0x16483099,0xbc00bbeb,0x3a0d3abc,0xb93cb852,0xb47bb080,0xbbaebbec,
0x3855393e,0xbababa0b,0xb850b69e,0xbabdbb49,0x3be93c00,0xb0be0000,0x335935f1,0xbbc9bb6e,0x3b373ba6,0xb6e8b4b1,0xac382d4c,0xbbfcbbf9,
0x39e33aa0,0xb96bb87c,0xb5b1b2d2,0xbb7abbd1,0x380a3905,0xbae8ba3b,0xb8eab7d8,0xba50baf9,0x3be73c00,0xb0f00000,0x319e3534,0xbbe0bb91,
0x3b273b9e,0xb72cb4e1,0xb042257f,0xbbeebc00,0x39b83a83,0xb999b8a6,0xb6ddb48d,0xbb3abbab,0x377a38c9,0xbb13ba69,0xb979b881,0xb9d6ba9c,
0x3be53c00,0xb1220000,0x2fbd3475,0xbbf1bbaf,0x3b163b97,0xb76fb511,0xb263a91b,0xbbd7bbfe,0x398b3a65,0xb9c5b8ce,0xb7feb5ab,0xbaeebb7b,
0x36dd388c,0xbb3aba95,0xb9fcb90e,0xb94fba33,0x3be33c00,0xb1530000,0x2c383365,0xbbfcbbc9,0x3b043b8f,0xb7b2b540,0xb43eae78,0xbbb7bbf6,
0x395d3a47,0xb9f0b8f6,0xb889b6c1,0xba97bb41,0x363c384d,0xbb5ebabf,0xba73b992,0xb8bcb9be,0x3be13c00,0xb1850000,0x217f31db,0xbc00bbdd,
0x3af13b86,0xb7f3b570,0xb546b12e,0xbb8ebbe5,0x392e3a27,0xba19b91d,0xb90cb7cd,0xba35bafc,0x3599380d,0xbb7fbae6,0xbadbba0b,0xb820b93e,
0x3bdf3c00,0xb1b60000,0xa9b1304e,0xbbfebbed,0x3ade3b7d,0xb81ab59f,0xb648b31b,0xbb5cbbcd,0x38fd3a07,0xba41b943,0xb986b867,0xb9c9baae,
0x34f33796,0xbb9cbb0b,0xbb35ba78,0xb6f4b8b5,0x3bdd3c00,0xb1e80000,0xae5f2d7e,0xbbf6bbf8,0x3acb3b74,0xb83ab5ce,0xb742b481,0xbb21bbad,
0x38cc39e5,0xba67b969,0xb9f8b8e2,0xb954ba56,0x344b3710,0xbbb5bb2e,0xbb7fbad9,0xb599b822,0x3bda3c00,0xb2190000,0xb0f028b6,0xbbe7bbff,
0x3ab63b6b,0xb85ab5fd,0xb81ab570,0xbadebb86,0x389939c3,0xba8cb98d,0xba60b956,0xb8d6b9f6,0x33403687,0xbbcbbb4e,0xbbb8bb2e,0xb432b710,
0x3bff3bff,0xa6ada648,0x3bfe3bff,0xa8e8a8b6,0x3bff3bff,0xa776a711,0x3bfe3bfe,0xa94da91b,0x3bff3bff,0xa81fa7da,0x3bfe3bfe,0xa9b1a97f,
0x3bff3bff,0xa884a852,0x3bfe3bfe,0xaa16a9e3,0x3bef3bf1,0xb029afd6,0x3bda3bdd,0xb219b1db,0x3bea3bed,0xb0a6b067,0x3bd43bd7,0xb294b257,
0x3be53be8,0xb122b0e4,0x3bce3bd1,0xb30fb2d2,0x3be03be3,0xb19eb160,0x3bc63bca,0xb389b34c,0x3bc83bce,0xb371b303,0x3b873b91,0xb56ab534,
0x3bba3bc1,0xb426b3df,0x3b733b7d,0xb5d4b59f,0x3bab3bb2,0xb493b45d,0x3b5e3b69,0xb63cb608,0x3b9a3ba2,0xb4ffb4c9,0x3b473b53,0xb6a4b670,
0x3b8b3b99,0xb552b505,0x3b073b1a,0xb7a6b75e,0x3b6f3b7d,0xb5ebb59f,0x3ade3af3,0xb81ab7ee,0x3b4f3b5f,0xb682b637,0x3ab33ac9,0xb85fb83d,
0x3b2c3b3e,0xb715b6cc,0x3a853a9c,0xb8a3b881,0x3b3a3b50,0xb6ddb67c,0x3a5c3a7c,0xb8dbb8b0,0x3b0a3b22,0xb79bb73d,0x3a193a3b,0xb92eb905,
0x3ad53af0,0xb82ab7f9,0x39d239f6,0xb97db956,0x3a9b3ab8,0xb884b858,0x398639ad,0xb9c9b9a4,0x3ad53af6,0xb82ab7e3,0x398b39ba,0xb9c5b996,
0x3a8c3ab1,0xb899b862,0x3929395b,0xba1db9f2,0x3a3d3a65,0xb902b8ce,0x38c138f6,0xba6fba47,0x39e73a13,0xb966b935,0x3855388c,0xbababa95,
0x3a5c3a8a,0xb8dbb89b,0x389938d8,0xba8cba5e,0x39f83a2b,0xb954b918,0x38153858,0xbae1bab8,0x398b39c3,0xb9c5b98d,0x371537a1,0xbb2cbb08,
0x39163951,0xba2db9fa,0x35f73687,0xbb6cbb4e,0x39d23a0f,0xb97db93a,0x371537b7,0xbb2cbb02,0x394f3992,0xb9fcb9be,0x35c83670,0xbb76bb53,
0x38c13909,0xba6fba37,0x346f351d,0xbbb0bb95,0x382a3877,0xbad5baa3,0x3219337d,0xbbdabbc7,0x39373984,0xba11b9cb,0x34cf3593,0xbba1bb80,
0x389438e7,0xba90ba52,0x327c3408,0xbbd6bbbe,0x37c8383d,0xbafebac9,0x2e9130e4,0xbbf5bbe8,0x36543710,0xbb59bb2e,0x16482aac,0xbc00bbfd,
0x388e38ec,0xba93ba4f,0x30d732a1,0xbbe8bbd4,0x3790382d,0xbb0dbad3,0x28e82e14,0xbbfebbf7,0x35eb36c1,0xbb6fbb41,0xaccea4b6,0xbbfabc00,
0x34323511,0xbbb8bb97,0xb201b036,0xbbdcbbee,0x37b23848,0xbb04bac2,0x96482bd9,0xbc00bbfc,0x35df36cc,0xbb71bb3e,0xb010ac1f,0xbbefbbfc,
0x33eb34ed,0xbbc0bb9d,0xb402b20d,0xbbbfbbdb,0x2fef31f4,0xbbf0bbdc,0xb5ebb4f9,0xbb6fbb9b,0x36313732,0xbb60bb25,0xb0f0ad7e,0xbbe7bbf8,
0x341a3529,0xbbbcbb93,0xb49fb31b,0xbba9bbcd,0x2fbd320d,0xbbf1bbdb,0xb6afb5ab,0xbb45bb7b,0xa4522aac,0xbc00bbfd,0xb850b7ac,0xbabdbb05,
0x349f35c2,0xbba9bb77,0xb4dbb365,0xbb9fbbc9,0x308d32ea,0xbbebbbd0,0xb715b5fd,0xbb2cbb6b,0x9fdb2c51,0xbc00bbfb,0xb894b812,0xba90bae3,
0xb109ad4c,0xbbe6bbf9,0xb982b90e,0xb9cdba33,0x32013444,0xbbdcbbb6,0xb721b5f1,0xbb2abb6e,0x26ad2edc,0xbbffbbf4,0xb8adb822,0xba7ebad9,
0xb05bab11,0xbbedbbfd,0xb9aab930,0xb9a6ba17,0xb4b7b2ea,0xbba5bbd0,0xba81ba1b,0xb8a8b92b,0x2d653179,0xbbf9bbe2,0xb89eb807,0xba89bae9,
0xadc99a48,0xbbf8bc00,0xb9afb92b,0xb9a1ba1b,0xb432b1aa,0xbbb8bbe0,0xba93ba27,0xb88eb91d,0xb6d2b587,0xbb3dbb82,0xbb45baf3,0xb6afb7ee,
0xa51b2cb5,0xbc00bbfa,0xb990b900,0xb9c0ba3f,0xb294af40,0xbbd4bbf3,0xba89ba13,0xb89eb935,0xb625b4bd,0xbb63bba4,0xbb47baf0,0xb6a4b7f9,
0xb865b780,0xbab0bb11,0xbbc5bb8f,0xb3a2b540,0xafefa648,0xbbf0bbff,0xba60b9dc,0xb8d6b972,0xb517b31b,0xbb96bbcd,0xbb35bad3,0xb6f4b82d,
0xb7feb693,0xbaeebb4b,0xbbc0bb84,0xb3ebb57c,0xb94ab8ab,0xba00ba7f,0xbbfdbbe9,0xaa7ab0cb,0xb340afd6,0xbbcbbbf1,0xbb0aba99,0xb79bb887,
0xb6d2b540,0xbb3dbb8f,0xbbaebb67,0xb47bb614,0xb8dbb828,0xba5cbad6,0xbbfbbbe0,0xac9cb1aa,0xba15b980,0xb933b9d0,0xbbecbbff,0x30742852,
0xb53ab303,0xbb90bbce,0xbb89bb30,0xb55eb705,0xb83ab6e3,0xbacbbb39,0xbbf2bbca,0xaf8bb34c,0xb9a1b8f6,0xb9afba47,0xbbf5bc00,0x2ec39e48,
0xbac1ba3b,0xb84ab905,0xbb92bbd0,0x352f32ea,0xb6c6b505,0xbb3fbb99,0xbbdcbba0,0xb201b4d5,0xb8fdb838,0xba41bacc,0xbbfebbfb,0x2a16ac83,
0xba50b9b1,0xb8eab99f,0xbbaebbe4,0x347b3147,0xbb4abad9,0xb699b822,0xbaf1bb5d,0x37f33642,0xb820b67c,0xbadbbb50,0xbbffbbe6,0xa884b115,
0xb9afb8f1,0xb9a1ba4b,0xbbd2bbf8,0x32c62db0,0xbae5ba56,0xb80fb8e2,0xbb2abb8c,0x3721354c,0xbbaebb58,0xb47bb659,0xba11baaa,0x3937386d,
0xb8d1b7e3,0xba64baf6,0xbbf2bc00,0x2f8ba248,0xba4db99b,0xb8eeb9b5,0xbb6fbbc1,0x35eb33df,0xbb5cbae3,0xb648b812,0xba6bbafc,0x38c737cd,
0xbbebbbb4,0xb08db451,0xb8f8b9be,0x3a453992,0xb974b89b,0xb9daba8a,0xbbb5bbed,0x344b304e,0xbad5ba33,0xb82ab90e,0xbad8bb58,0x38253659,
0xbbb3bb55,0xb457b665,0xb979ba37,0x39d63909,0xbc00bbed,0x9648b067,0xb764b8a0,0x3b183a87,0xba09b93a,0xb941ba0f,0xbb4abbaf,0x36993475,
0xbb45bab8,0xb6afb858,0xba11babf,0x3937384d,0xbbeabbab,0xb0a6b48d,0xb85ab943,0x3ab63a07,0xbbecbc00,0x30749a48,0xb493b6b5,0x3bab3b43,
0xba8cb9cb,0xb899b984,0xbab3bb46,0x385f36aa,0xbb9cbb28,0xb4f3b726,0xb91fb9fa,0x3a253951,0xbc00bbe4,0xa452b147,0xb631b828,0x3b603ad6,
0xbbb0bbee,0x346f3036,0xae5fb3df,0x3bf63bc1,0xbafeba4f,0xb7c8b8ec,0xb9f4bab5,0x3958385d,0xbbd8bb82,0xb24bb587,0xb80ab90e,0x3ae83a33,
0xbbf3bbfe,0x2f27a97f,0xb2f7b5da,0x3bcf3b72,0xbb4cbbb7,0x368d3438,0x2dc9ac1f,0x3bf83bfc,0xbb5cbac2,0xb648b848,0xb911b9fe,0x3a31394d,
0xbbf9bbc4,0xad33b3ae,0xb5b1b802,0x3b7a3aed,0xbbc5bbf9,0x33a22d1a,0xa94db26f,0x3bfe3bd6,0xbac4bb5d,0x38453642,0x346f2fa4,0x3bb03bf1,
0xbba5bb25,0xb4b7b732,0xb80fb927,0x3ae53a1f,0xbbffbbee,0x2884b036,0xb24bb5b6,0x3bd83b79,0xbb76bbd6,0x35c8326f,0x305ba7da,0x3bed3bff,
0xba19bae0,0x392e3817,0x374234c9,0x3b213ba2,0xbbd9bb77,0xb232b5c2,0xb5ebb832,0x3b6f3ad0,0xbbe8bc00,0x30d7a57f,0xa81fb288,0x3bff3bd5,
0xbb07bb95,0x37a6351d,0x34f33080,0x3b9c3bec,0xb94fba43,0x39fc38fb,0x38ea3780,0x3a503b11,0xbbf8bbb6,0xadc9b444,0xb328b64e,0x3bcc3b5a,
0xbbb7bbf8,0x343e2db0,0x3042a9e3,0x3bee3bfe,0xba7abb36,0x38b236ee,0x379034ed,0x3b0d3b9d,0xb86ab989,0x3aac39c7,0x3a0438fb,0x39463a43,
0xbc00bbe2,0x2311b179,0xac9cb414,0x3bfb3bbc,0xbb6abbd7,0x36023257,0x34b72f40,0x3ba53bf3,0xb9d2babc,0x397d3852,0x38f83775,0x3a453b14,
0xb6ddb8b5,0x3b3a3a78,0x3ae83a0b,0x380a393e,0xbbf2bbfa,0x2f8bacb5,0x2d33af0e,0x3bf93bf4,0xbb04bb9e,0x37b234e1,0x372c3451,0x3b273bb4,
0xb911ba27,0x3a31391d,0x3a0038e2,0x394a3a56,0xb4c3b796,0x3ba33b0b,0x3b8b3ae6,0x3552380d,0x4c004c00,0x26480000,0x4c004c00,0x33113248,
0x4c004c00,0x2cb62a48,0x4c004c00,0x345233db,0x4c004c00,0x2fdb2e48,0x4c004c00,0x351b34b6,0x4c004c00,0x317f30b6,0x4bff4c00,0x35e4357f,
0x4c004c00,0x2fdb0000,0x4bfb4bfc,0x3c6a3bd9,0x4bff4c00,0x35e433db,0x4bf94bfa,0x3d653ce7,0x4bfe4bff,0x38e837da,0x4bf64bf7,0x3e5f3de2,
0x4bfd4bfe,0x3ade39e3,0x4bf24bf4,0x3f593edc,0x4c004c00,0x33110000,0x4bf04bf4,0x3fef3f0e,0x4bfe4bff,0x394d3711,0x4be84bed,0x40d74067,
0x4bfb4bfd,0x3c6a3b11,0x4bdf4be4,0x41b64147,0x4bf64bf9,0x3e2d3d4c,0x4bd44bda,0x42944226,0x4c004c00,0x351b0000,0x4bdf4be6,0x41b64115,
0x4bfc4bfe,0x3ba7391b,0x4bcf4bd7,0x42f74257,0x4bf64bf9,0x3e5f3d1a,0x4bbc4bc6,0x441a4396,0x4bec4bf1,0x40743fa4,0x4ba54bb1,0x44b74469,
0x4bff4c00,0x36ad0000,0x4bc84bd4,0x437142a1,0x4bfa4bfd,0x3d003aac,0x4bac4bbb,0x44874420,0x4bef4bf5,0x40293eaa,0x4b8b4b9d,0x455244ed,
0x4bde4be7,0x41cf40fd,0x4b654b79,0x461a45b6,0x4bff4c00,0x381f0000,0x4bab4bbc,0x44934414,0x4bf64bfc,0x3e2d3c1f,0x4b814b97,0x458d4511,
0x4be54bef,0x4122401d,0x4b4f4b69,0x46824608,0x4bcc4bda,0x43284226,0x4b164b33,0x476f46f9,0x4bfe4c00,0x38e80000,0x4b874ba0,0x456a44d5,
0x4bf24bfa,0x3f593ce7,0x4b4c4b6b,0x468d45fd,0x4bda4be8,0x421940e4,0x4b074b2b,0x47a6471b,0x4bb74bca,0x443e434c,0x4ab64ae0,0x485a4817,
0x4bfe4c00,0x39b10000,0x4b5e4b80,0x463c4593,0x4bee4bf8,0x40423db0,0x4b104b39,0x478546e3,0x4bce4be0,0x430f41aa,0x4ab34ae3,0x485f4812,
0x4b9e4bb7,0x44e74438,0x4a494a7f,0x48f348ab,0x4bfd4c00,0x3a7a0000,0x4b2f4b5a,0x470a464e,0x4be84bf6,0x40d73e78,0x4acb4aff,0x483a47c2,
0x4bbf4bd6,0x4402426f,0x4a544a92,0x48e54891,0x4b814ba2,0x458d44c9,0x49cd4a13,0x49824935,0x4bfd4c00,0x3b430000,0x4afb4b30,0x47d24705,
0x4be24bf3,0x416c3f40,0x4a7e4abf,0x48ad484d,0x4bae4bcb,0x447b4334,0x49eb4a37,0x49624909,0x4b604b8a,0x46314558,0x4946499b,0x4a0449b5,
0x4bfc4c00,0x3c060000,0x4ac14b02,0x484a47b7,0x4bdc4bf0,0x42014004,0x4a294a78,0x491b48b5,0x4b9c4bc0,0x44f343f7,0x497949d4,0x49d6497b,
0x4b3d4b70,0x46d245e5,0x48b24918,0x4a7a4a2b,0x4bfb4c00,0x3c6a0000,0x4a814ad0,0x48a84832,0x4bd44bed,0x42944067,0x49cd4a2b,0x49824918,
0x4b874bb2,0x456a445d,0x48fd4969,0x4a4149e5,0x4b164b53,0x476f4670,0x4815488c,0x4ae14a95,0x4bfa4c00,0x3cce0000,0x4a3d4a99,0x49024887,
0x4bcc4be9,0x432840cb,0x496b49d8,0x49e34976,0x4b714ba4,0x45df44bd,0x487a48f6,0x4aa24a47,0x4aeb4b33,0x480546f9,0x46dd47ee,0x4b3a4af3,
0x4bf94c00,0x3d330000,0x49f44a5e,0x495848d8,0x4bc34be5,0x43ba412e,0x49024980,0x4a3d49d0,0x4b594b95,0x4654451d,0x47dd487c,0x4af74aa0,
0x4abd4b11,0x48504780,0x458146b5,0x4b834b43,0x4bf84c00,0x3d970000,0x49a64a1f,0x49aa4927,0x4bba4be1,0x44264191,0x48944922,0x4a904a23,
0x4b3f4b84,0x46c6457c,0x46bb47f9,0x4b424af0,0x4a8c4aed,0x48994802,0x441a4570,0x4bbc4b86,0x4bf74c00,0x3dfb0000,0x495449dc,0x49f84972,
0x4bb04bdc,0x446f41f4,0x482048bf,0x4adb4a71,0x4b244b72,0x473745da,0x458d46ee,0x4b814b36,0x4a584ac6,0x48e04842,0x41534420,0x4be34bbb,
0x4bf64c00,0x3e5f0000,0x48fd4996,0x4a4149ba,0x4ba54bd7,0x44b74257,0x474e4858,0x4b1e4ab8,0x4b074b5f,0x47a64637,0x445745da,0x4bb34b72,
0x4a214a9c,0x49244881,0x3cce4191,0x4bfa4be1,0x4bf54c00,0x3ec30000,0x48a3494d,0x4a8549fe,0x4b9a4bd2,0x44ff42b9,0x465447d8,0x4b594af9,
0x4ae84b4b,0x480a4693,0x423244bd,0x4bd94ba4,0x49e74a71,0x496648bf,0xb4523db0,0x4c004bf8,0x4bf34c00,0x3f270000,0x48454900,0x4ac44a3f,
0x4b8e4bcd,0x4546431b,0x455246f9,0x4b8b4b33,0x4ac74b36,0x484046ee,0x3f594334,0x4bf24bcb,0x49aa4a43,0x49a648fb,0xbef52a48,0x4bf44c00,
0x4bf24c00,0x3f8b0000,0x47c848b0,0x4afe4a7c,0x4b814bc7,0x458d437d,0x444b4614,0x4bb54b67,0x4aa54b20,0x48744748,0x388440e4,0x4bff4be8,
0x496b4a13,0x49e34935,0xc263bd4c,0x4bd74bf9,0x4bf04c00,0x3fef0000,0x46ff485d,0x4b324ab5,0x4b734bc1,0x45d443df,0x427c4529,0x4bd64b93,
0x4a814b08,0x48a847a1,0xb9b13d1a,0x4bfe4bf9,0x492949e1,0x4a1d496d,0xc49fc160,0x4ba94be3,0x4bef4c00,0x40290000,0x46314807,0x4b604ae9,
0x4b654bbb,0x461a4420,0x405b4438,0x4bed4bb7,0x4a5c4af0,0x48db47f9,0xbfef2e48,0x4bf04c00,0x48e549ad,0x4a5449a4,0xc602c408,0x4b6a4bbe,
0x4bed4c00,0x405b0000,0x455e475e,0x4b894b1a,0x4b574bb4,0x465f4451,0x3c6a4288,0x4bfb4bd5,0x4a354ad6,0x490c4828,0xc27cbc51,0x4bd64bfb,
0x489e4976,0x4a8949d8,0xc759c558,0x4b1b4b8a,0x4beb4c00,0x408d0000,0x448746aa,0x4bac4b46,0x4b474bad,0x46a44481,0x26484099,0x4c004beb,
0x4a0d4abc,0x493c4852,0xc47bc080,0x4bae4bec,0x4855493e,0x4aba4a0b,0xc850c69e,0x4abd4b49,0x4be94c00,0x40be0000,0x435945f1,0x4bc94b6e,
0x4b374ba6,0x46e844b1,0xbc383d4c,0x4bfc4bf9,0x49e34aa0,0x496b487c,0xc5b1c2d2,0x4b7a4bd1,0x480a4905,0x4ae84a3b,0xc8eac7d8,0x4a504af9,
0x4be74c00,0x40f00000,0x419e4534,0x4be04b91,0x4b274b9e,0x472c44e1,0xc042357f,0x4bee4c00,0x49b84a83,0x499948a6,0xc6ddc48d,0x4b3a4bab,
0x477a48c9,0x4b134a69,0xc979c881,0x49d64a9c,0x4be54c00,0x41220000,0x3fbd4475,0x4bf14baf,0x4b164b97,0x476f4511,0xc263b91b,0x4bd74bfe,
0x498b4a65,0x49c548ce,0xc7fec5ab,0x4aee4b7b,0x46dd488c,0x4b3a4a95,0xc9fcc90e,0x494f4a33,0x4be34c00,0x41530000,0x3c384365,0x4bfc4bc9,
0x4b044b8f,0x47b24540,0xc43ebe78,0x4bb74bf6,0x495d4a47,0x49f048f6,0xc889c6c1,0x4a974b41,0x463c484d,0x4b5e4abf,0xca73c992,0x48bc49be,
0x4be14c00,0x41850000,0x317f41db,0x4c004bdd,0x4af14b86,0x47f34570,0xc546c12e,0x4b8e4be5,0x492e4a27,0x4a19491d,0xc90cc7cd,0x4a354afc,
0x4599480d,0x4b7f4ae6,0xcadbca0b,0x4820493e,0x4bdf4c00,0x41b60000,0xb9b1404e,0x4bfe4bed,0x4ade4b7d,0x481a459f,0xc648c31b,0x4b5c4bcd,
0x48fd4a07,0x4a414943,0xc986c867,0x49c94aae,0x44f34796,0x4b9c4b0b,0xcb35ca78,0x46f448b5,0x4bdd4c00,0x41e80000,0xbe5f3d7e,0x4bf64bf8,
0x4acb4b74,0x483a45ce,0xc742c481,0x4b214bad,0x48cc49e5,0x4a674969,0xc9f8c8e2,0x49544a56,0x444b4710,0x4bb54b2e,0xcb7fcad9,0x45994822,
0x4bda4c00,0x42190000,0xc0f038b6,0x4be74bff,0x4ab64b6b,0x485a45fd,0xc81ac570,0x4ade4b86,0x489949c3,0x4a8c498d,0xca60c956,0x48d649f6,
0x43404687,0x4bcb4b4e,0xcbb8cb2e,0x44324710,0x4bd84c00,0x424b0000,0xc2adb248,0x4bd34c00,0x4aa24b62,0x487a462b,0xc88ec659,0x4a934b58,
0x4865499f,0x4ab049b1,0xcabdc9c3,0x4850498d,0x41e845fd,0x4bdd4b6b,0xcbe1cb74,0x418545ce,0x4bd64c00,0x427c0000,0xc432bbd9,0x4bb84bfc,
0x4a8c4b58,0x48994659,0xc8fdc73d,0x4a414b22,0x4830497b,0x4ad149d4,0xcb10ca27,0x4785491d,0x408d4570,0x4beb4b86,0xcbf9cbad,0x3d334481,
0x4bd34c00,0x42ad0000,0xc50bbf0e,0x4b984bf4,0x4a764b4e,0x48b74687,0xc966c80d,0x49e74ae6,0x47f34956,0x4af149f6,0xcb57ca83,0x465f48a6,
0x3e5f44e1,0x4bf64b9e,0xcc00cbd7,0xb17f4257,0x4bd04c00,0x42de0000,0xc5dfc115,0x4b714be6,0x4a604b43,0x48d646b5,0xc9c9c877,0x49864aa3,
0x47854930,0x4b104a17,0xcb92cad6,0x452f4828,0x3b434451,0x4bfd4bb4,0xcbf5cbf3,0xbe913f40,0x4bce4c00,0x430f0000,0xc6afc2a1,0x4b454bd4,
0x4a494b39,0x48f346e3,0xca25c8dd,0x491f4a5a,0x47154909,0x4b2c4a37,0xcbc0cb20,0x43eb4748,0x3311437d,0x4c004bc7,0xcbd9cbff,0xc2323711,
0x4bcb4c00,0x43400000,0xc77ac414,0x4b134bbc,0x4a314b2e,0x49114710,0xca7ac93e,0x48b24a0b,0x46a448e2,0x4b474a56,0xcbe2cb5f,0x416c4637,
0xb7764257,0x4bff4bd7,0xcbaccbfd,0xc487bb75,0x4bc84c00,0x43710000,0xc820c4d5,0x4adb4ba0,0x4a194b22,0x492e473d,0xcac7c99b,0x484049b5,
0x463148ba,0x4b604a74,0xcbf8cb95,0x3dc9451d,0xbc9c412e,0x4bfb4be5,0xcb6fcbeb,0xc5ebc099,0x4bc54c00,0x43a20000,0xc87fc593,0x4a9e4b80,
0x4a004b17,0x494a476a,0xcb0dc9f2,0x4790495b,0x45bc4891,0x4b784a92,0xcc00cbc0,0x317f43f7,0xbf594004,0x4bf24bf0,0xcb21cbca,0xc742c34c,
0x4bc24c00,0x43d30000,0xc8dbc64e,0x4a5c4b5a,0x49e74b0b,0x49664796,0xcb4aca43,0x469948fb,0x45464867,0x4b8e4aae,0xcbfbcbe0,0xbc6a41aa,
0xc1093db0,0x4be64bf8,0xcac4cb9b,0xc845c4f9,0x4bbf4c00,0x44020000,0xc933c705,0x4a154b30,0x49cd4aff,0x498247c2,0xcb7fca8e,0x45994896,
0x44cf483d,0x4ba14ac9,0xcbe9cbf5,0xc0be3eaa,0xc2633aac,0x4bd74bfd,0xca58cb5d,0xc8e0c642,0x4bbc4c00,0x441a0000,0xc986c7b7,0x49c94b02,
0x49b34af3,0x499d47ee,0xcbabcad3,0x4493482d,0x44574812,0x4bb34ae3,0xcbcbcbff,0xc34037da,0xc3ba33db,0x4bc34c00,0xc9dfcb11,0xc970c780,
0x4bb84c00,0x44320000,0xc9d6c832,0x49794ad0,0x49994ae6,0x49b8480d,0xcbcecb11,0x430f4780,0x43ba47cd,0x4bc34afc,0xcb9fcbfe,0xc4dbb97f,
0xc487b57f,0x4bac4c00,0xc958cab8,0xc9f4c858,0x4bb54c00,0x444b0000,0xca21c887,0x49244a99,0x497d4ad9,0x49d24822,0xcbe7cb49,0x40f0469e,
0x42c64775,0x4bd24b14,0xcb68cbf2,0xc60ebf72,0xc52fbb75,0x4b924bfd,0xc8c7ca52,0xca6bc8e7,0x4bb24c00,0x44630000,0xca67c8d8,0x48cc4a5e,
0x49624acc,0x49eb4838,0xcbf8cb79,0x3d9745b6,0x41cf471b,0x4bde4b2b,0xcb24cbdb,0xc737c20d,0xc5d4be14,0x4b734bf7,0xc82ac9e1,0xcad5c96d,
0x4bae4c00,0x447b0000,0xcaa9c927,0x486f4a1f,0x49464abf,0x4a04484d,0xcc00cba2,0x351b44c9,0x40d746c1,0x4be84b41,0xcad5cbb9,0xc82ac42c,
0xc676c036,0x4b524bee,0xc70ac964,0xcb2fc9e9,0x4bab4c00,0x44930000,0xcae5c972,0x480f49dc,0x49294ab1,0x4a1d4862,0xcbfecbc4,0xba1643ae,
0x3fbd4665,0x4bf14b55,0xca7acb8c,0xc8b2c54c,0xc715c160,0x4b2c4be3,0xc5b1c8dd,0xcb7aca5a,0x4ba74c00,0x44ab0000,0xcb1bc9ba,0x47594996,
0x490c4aa3,0x4a354877,0xcbf2cbdf,0xbf5941c3,0x3dc94608,0x4bf84b69,0xca15cb55,0xc933c665,0xc7b2c288,0x4b044bd5,0xc44bc84d,0xcbb5cabf,
0x4ba34c00,0x44c30000,0xcb4cc9fe,0x468d494d,0x48ee4a95,0x4a4d488c,0xcbdecbf1,0xc1cf3fa4,0x3ba745ab,0x4bfc4b7b,0xc9a6cb14,0xc9aac775,
0xc825c3ae,0x4ad84bc4,0xc1b6c76a,0xcbdfcb17,0x4b9f4c00,0x44db0000,0xcb78ca3f,0x45bc4900,0x48d14a87,0x4a6448a0,0xcbc0cbfd,0xc3eb3b75,
0x3776454c,0x4bff4b8c,0xc92ecac9,0xca19c83d,0xc86fc469,0x4aa94bb1,0xbd97c62b,0xcbf8cb62,0x4b9c4c00,0x44f30000,0xcb9eca7c,0x44e748b0,
0x48b24a78,0x4a7a48b5,0xcb9acc00,0xc4ffaa48,0xa64844ed,0x4c004b9d,0xc8adca74,0xca7ec8ba,0xc8b7c4f9,0x4a764b9b,0x2cb6c4e1,0xcc00cb9e,
0x4b984c00,0x450b0000,0xcbbdcab5,0x440e485d,0x48944a69,0x4a9048c9,0xcb6acbfc,0xc602bc1f,0xb81f448d,0x4bff4bab,0xc825ca17,0xcad8c930,
0xc8fdc587,0x4a414b82,0x3e2dc31b,0xcbf6cbcd,0x4b944c00,0x45230000,0xcbd7cae9,0x42634807,0x48744a5a,0x4aa548dd,0xcb32cbf0,0xc6ffc004,
0xbc06442c,0x4bfc4bb9,0xc72cc9b1,0xcb27c99f,0xc941c614,0x4a094b67,0x4201c067,0xcbdccbed,0x4b904c00,0x453a0000,0xcbeacb1a,0x40a6475e,
0x48554a4b,0x4aba48f1,0xcaf1cbdc,0xc7f3c1f4,0xbdfb4396,0x4bf74bc6,0xc602c943,0xcb6aca07,0xc982c69e,0x49cd4b49,0x446fbaac,0xcbb0cbfd,
0x4b8b4c00,0x45520000,0xcbf8cb46,0x3dc946aa,0x48354a3b,0x4ace4905,0xcaa9cbc1,0xc86fc3df,0xbfef42d2,0x4bf04bd1,0xc4cfc8ce,0xcba1ca65,
0xc9c0c726,0x49904b28,0x45d43852,0xcb73cbff,0x4b874c00,0x456a0000,0xcbffcb6e,0x388445f1,0x48154a2b,0x4ae14918,0xca58cb9e,0xc8e0c4e1,
0xc0f0420d,0x4be74bdb,0xc328c852,0xcbcccabc,0xc9fcc7ac,0x494f4b05,0x472c3fa4,0xcb27cbf1,0x4b834c00,0x45810000,0xcc00cb91,0xb51b4534,
0x47e84a1b,0x4af4492b,0xca00cb74,0xc94ac5ce,0xc1e84147,0x4bdd4be4,0xc0a6c7a1,0xcbeacb08,0xca35c817,0x490c4ae0,0x483a4288,0xcacbcbd5,
0x4b7f4c00,0x45990000,0xcbfacbaf,0xbcce4475,0x47a64a0b,0x4b07493e,0xc9a1cb43,0xc9afc6b5,0xc2de4080,0x4bd04bec,0xbc38c693,0xcbfccb4b,
0xca6bc858,0x48c74ab8,0x48d64499,0xca60cbaa,0x4b7a4c00,0x45b10000,0xcbefcbc9,0xc0294365,0x476449fa,0x4b184951,0xc93ccb0b,0xca0dc796,
0xc3d33f72,0x4bc24bf2,0x3311c57c,0xcc00cb84,0xca9ec896,0x487f4a8e,0x496645e5,0xc9e7cb70,0x4b764c00,0x45c80000,0xcbddcbdd,0xc1e841db,
0x472149e9,0x4b2a4964,0xc8d1cacc,0xca64c838,0xc4633de2,0x4bb24bf7,0x3dfbc45d,0xcbf7cbb2,0xcacec8d3,0x48354a62,0x49eb4726,0xc962cb28,
0x4b714c00,0x45df0000,0xcbc5cbed,0xc3a2404e,0x46dd49d8,0x4b3a4976,0xc85fca87,0xcab3c8a0,0xc4db3c51,0x4b9f4bfb,0x4185c26f,0xcbe1cbd6,
0xcafbc90e,0x47d24a33,0x4a64482d,0xc8d1cad3,0x4b6c4c00,0x45f70000,0xcba7cbf8,0xc4ab3d7e,0x469949c7,0x4b4a4989,0xc7d2ca3b,0xcafbc905,
0xc552397f,0x4b8b4bfe,0x4402c01d,0xcbbfcbef,0xcb24c948,0x47374a02,0x4ace48bf,0xc835ca71,0x4b684c00,0x460e0000,0xcb83cbff,0xc58138b6,
0x465449b5,0x4b59499b,0xc6ddc9e9,0xcb3ac964,0xc5c834b6,0x4b764c00,0x453abb11,0xcb90cbfd,0xcb4ac980,0x469949d0,0x4b2a4948,0xc721ca02,
0x2c002c00,0x2c002c00,0x2c002c00,0x2c002c00,0x2b642c00,0x261f29a8,0xa61f0000,0xab64a9a8,0x29a82c00,0xa9a80000,0xa9a8ac00,0x29a80000,
0x261f2c00,0xab64a9a8,0x2b640000,0xa61f29a8,0x2c00,0xac00,0x2c00,0xac00,0xa61f2c00,0x2b64a9a8,0xab640000,0x261f29a8,
0xa9a82c00,0x29a80000,0x29a8ac00,0xa9a80000,0xab642c00,0xa61f29a8,0x261f0000,0x2b64a9a8,0,0,0,0,
0x261f0000,0x2b6429a8,0x2b642c00,0x261f29a8,0x29a80000,0x29a82c00,0xa9a80000,0xa9a8ac00,0x2b640000,0xa61f29a8,0xa61fac00,0x2b6429a8,
0x2c000000,0xac000000,0x2c000000,0xac000000,0x2b640000,0xa61fa9a8,0xa61f2c00,0x2b64a9a8,0x29a80000,0x29a8ac00,0xa9a80000,0xa9a82c00,
0x261f0000,0x2b64a9a8,0x2b64ac00,0x261fa9a8,0xac002c00,0xac002c00,0xac002c00,0xac002c00,0xab642c00,0xa61f29a8,0x261f0000,0x2b64a9a8,
0xa9a82c00,0x29a80000,0x29a8ac00,0xa9a80000,0xa61f2c00,0x2b64a9a8,0xab640000,0x261f29a8,0x2c00,0xac00,0x2c00,0xac00,
0x261f2c00,0xab64a9a8,0x2b640000,0xa61f29a8,0x29a82c00,0xa9a80000,0xa9a8ac00,0x29a80000,0x2b642c00,0x261f29a8,0xa61f0000,0xab64a9a8,
0,0,0,0,0xa61f0000,0xab6429a8,0xab642c00,0xa61f29a8,0xa9a80000,0xa9a82c00,0x29a80000,0x29a8ac00,
0xab640000,0x261f29a8,0x261fac00,0xab6429a8,0xac000000,0x2c000000,0xac000000,0x2c000000,0xab640000,0x261fa9a8,0x261f2c00,0xab64a9a8,
0xa9a80000,0xa9a8ac00,0x29a80000,0x29a82c00,0xa61f0000,0xab64a9a8,0xab64ac00,0xa61fa9a8,0,0,0,0,
0xa61f0000,0xab64a9a8,0xab64ac00,0xa61fa9a8,0xa9a80000,0xa9a8ac00,0x29a80000,0x29a82c00,0xab640000,0x261fa9a8,0x261f2c00,0xab64a9a8,
0xac000000,0x2c000000,0xac000000,0x2c000000,0xab640000,0x261f29a8,0x261fac00,0xab6429a8,0xa9a80000,0xa9a82c00,0x29a80000,0x29a8ac00,
0xa61f0000,0xab6429a8,0xab642c00,0xa61f29a8,0x2c002c00,0x2c002c00,0x2c002c00,0x2c002c00,0x2b642c00,0x261f29a8,0xa61f0000,0xab64a9a8,
0x29a82c00,0xa9a80000,0xa9a8ac00,0x29a80000,0x261f2c00,0xab64a9a8,0x2b640000,0xa61f29a8,0x2c00,0xac00,0x2c00,0xac00,
0xa61f2c00,0x2b64a9a8,0xab640000,0x261f29a8,0xa9a82c00,0x29a80000,0x29a8ac00,0xa9a80000,0xab642c00,0xa61f29a8,0x261f0000,0x2b64a9a8,
0,0,0,0,0x261f0000,0x2b64a9a8,0x2b64ac00,0x261fa9a8,0x29a80000,0x29a8ac00,0xa9a80000,0xa9a82c00,
0x2b640000,0xa61fa9a8,0xa61f2c00,0x2b64a9a8,0x2c000000,0xac000000,0x2c000000,0xac000000,0x2b640000,0xa61f29a8,0xa61fac00,0x2b6429a8,
0x29a80000,0x29a82c00,0xa9a80000,0xa9a8ac00,0x261f0000,0x2b6429a8,0x2b642c00,0x261f29a8,0xac002c00,0xac002c00,0xac002c00,0xac002c00,
0xab642c00,0xa61f29a8,0x261f0000,0x2b64a9a8,0xa9a82c00,0x29a80000,0x29a8ac00,0xa9a80000,0xa61f2c00,0x2b64a9a8,0xab640000,0x261f29a8,
0x2c00,0xac00,0x2c00,0xac00,0x261f2c00,0xab64a9a8,0x2b640000,0xa61f29a8,0x29a82c00,0xa9a80000,0xa9a8ac00,0x29a80000,
0x2b642c00,0x261f29a8,0xa61f0000,0xab64a9a8,0x2c002c00,0x2c002c00,0x2c002c00,0x2c002c00,0xab64ac00,0xa61fa9a8,0x261f0000,0x2b6429a8,
0x29a82c00,0xa9a80000,0xa9a8ac00,0x29a80000,0xa61fac00,0x2b6429a8,0xab640000,0x261fa9a8,0x2c00,0xac00,0x2c00,0xac00,
0x261fac00,0xab6429a8,0x2b640000,0xa61fa9a8,0xa9a82c00,0x29a80000,0x29a8ac00,0xa9a80000,0x2b64ac00,0x261fa9a8,0xa61f0000,0xab6429a8,
0,0,0,0,0xa61f0000,0xab64a9a8,0xab64ac00,0xa61fa9a8,0x29a80000,0x29a82c00,0xa9a80000,0xa9a8ac00,
0xab640000,0x261fa9a8,0x261f2c00,0xab64a9a8,0x2c000000,0xac000000,0x2c000000,0xac000000,0xab640000,0x261f29a8,0x261fac00,0xab6429a8,
0x29a80000,0x29a8ac00,0xa9a80000,0xa9a82c00,0xa61f0000,0xab6429a8,0xab642c00,0xa61f29a8,0xac002c00,0xac002c00,0xac002c00,0xac002c00,
0x2b64ac00,0x261fa9a8,0xa61f0000,0xab6429a8,0xa9a82c00,0x29a80000,0x29a8ac00,0xa9a80000,0x261fac00,0xab6429a8,0x2b640000,0xa61fa9a8,
0x2c00,0xac00,0x2c00,0xac00,0xa61fac00,0x2b6429a8,0xab640000,0x261fa9a8,0x29a82c00,0xa9a80000,0xa9a8ac00,0x29a80000,
0xab64ac00,0xa61fa9a8,0x261f0000,0x2b6429a8,0,0,0,0,0x261f0000,0x2b64a9a8,0x2b64ac00,0x261fa9a8,
0xa9a80000,0xa9a82c00,0x29a80000,0x29a8ac00,0x2b640000,0xa61fa9a8,0xa61f2c00,0x2b64a9a8,0xac000000,0x2c000000,0xac000000,0x2c000000,
0x2b640000,0xa61f29a8,0xa61fac00,0x2b6429a8,0xa9a80000,0xa9a8ac00,0x29a80000,0x29a82c00,0x261f0000,0x2b6429a8,0x2b642c00,0x261f29a8,
0,0,0,0,0x261f0000,0x2b6429a8,0x2b642c00,0x261f29a8,0xa9a80000,0xa9a8ac00,0x29a80000,0x29a82c00,
0x2b640000,0xa61f29a8,0xa61fac00,0x2b6429a8,0xac000000,0x2c000000,0xac000000,0x2c000000,0x2b640000,0xa61fa9a8,0xa61f2c00,0x2b64a9a8,
0xa9a80000,0xa9a82c00,0x29a80000,0x29a8ac00,0x261f0000,0x2b64a9a8,0x2b64ac00,0x261fa9a8,0x2c002c00,0x2c002c00,0x2c002c00,0x2c002c00,
0xab64ac00,0xa61fa9a8,0x261f0000,0x2b6429a8,0x29a82c00,0xa9a80000,0xa9a8ac00,0x29a80000,0xa61fac00,0x2b6429a8,0xab640000,0x261fa9a8,
0x2c00,0xac00,0x2c00,0xac00,0x261fac00,0xab6429a8,0x2b640000,0xa61fa9a8,0xa9a82c00,0x29a80000,0x29a8ac00,0xa9a80000,
0x2b64ac00,0x261fa9a8,0xa61f0000,0xab6429a8,0,0,0,0,0xa61f0000,0xab6429a8,0xab642c00,0xa61f29a8,
0x29a80000,0x29a8ac00,0xa9a80000,0xa9a82c00,0xab640000,0x261f29a8,0x261fac00,0xab6429a8,0x2c000000,0xac000000,0x2c000000,0xac000000,
0xab640000,0x261fa9a8,0x261f2c00,0xab64a9a8,0x29a80000,0x29a82c00,0xa9a80000,0xa9a8ac00,0xa61f0000,0xab64a9a8,0xab64ac00,0xa61fa9a8,
0xac002c00,0xac002c00,0xac002c00,0xac002c00,0x2b64ac00,0x261fa9a8,0xa61f0000,0xab6429a8,0xa9a82c00,0x29a80000,0x29a8ac00,0xa9a80000,
0x261fac00,0xab6429a8,0x2b640000,0xa61fa9a8,0x2c00,0xac00,0x2c00,0xac00,0xa61fac00,0x2b6429a8,0xab640000,0x261fa9a8,
0x29a82c00,0xa9a80000,0xa9a8ac00,0x29a80000,0xab64ac00,0xa61fa9a8,0x261f0000,0x2b6429a8,0x2bd92c00,0x2aa72b64,0x287229a8,0x223e261f,
0x2aa72c00,0xa23e261f,0xabd9a9a8,0xa872ab64,0x28722c00,0xabd9a61f,0x223ea9a8,0x2aa72b64,0x223e2c00,0xa872ab64,0x2aa729a8,0xabd9a61f,
0xa23e2c00,0x2872ab64,0xaaa729a8,0x2bd9a61f,0xa8722c00,0x2bd9a61f,0xa23ea9a8,0xaaa72b64,0xaaa72c00,0x223e261f,0x2bd9a9a8,0x2872ab64,
0xabd92c00,0xaaa72b64,0xa87229a8,0xa23e261f,0x223e0000,0x2872261f,0x2aa729a8,0x2bd92b64,0x28720000,0x2bd92b64,0x223e29a8,0xaaa7a61f,
0x2aa70000,0x223e2b64,0xabd9a9a8,0x2872a61f,0x2bd90000,0xaaa7261f,0x2872a9a8,0xa23e2b64,0x2bd90000,0xaaa7a61f,0x287229a8,0xa23eab64,
0x2aa70000,0x223eab64,0xabd929a8,0x2872261f,0x28720000,0x2bd9ab64,0x223ea9a8,0xaaa7261f,0x223e0000,0x2872a61f,0x2aa7a9a8,0x2bd9ab64,
0xabd92c00,0xaaa72b64,0xa87229a8,0xa23e261f,0xaaa72c00,0x223e261f,0x2bd9a9a8,0x2872ab64,0xa8722c00,0x2bd9a61f,0xa23ea9a8,0xaaa72b64,
0xa23e2c00,0x2872ab64,0xaaa729a8,0x2bd9a61f,0x223e2c00,0xa872ab64,0x2aa729a8,0xabd9a61f,0x28722c00,0xabd9a61f,0x223ea9a8,0x2aa72b64,
0x2aa72c00,0xa23e261f,0xabd9a9a8,0xa872ab64,0x2bd92c00,0x2aa72b64,0x287229a8,0x223e261f,0xa23e0000,0xa872261f,0xaaa729a8,0xabd92b64,
0xa8720000,0xabd92b64,0xa23e29a8,0x2aa7a61f,0xaaa70000,0xa23e2b64,0x2bd9a9a8,0xa872a61f,0xabd90000,0x2aa7261f,0xa872a9a8,0x223e2b64,
0xabd90000,0x2aa7a61f,0xa87229a8,0x223eab64,0xaaa70000,0xa23eab64,0x2bd929a8,0xa872261f,0xa8720000,0xabd9ab64,0xa23ea9a8,0x2aa7261f,
0xa23e0000,0xa872a61f,0xaaa7a9a8,0xabd9ab64,0xa23e0000,0xa872a61f,0xaaa7a9a8,0xabd9ab64,0xa8720000,0xabd9ab64,0xa23ea9a8,0x2aa7261f,
0xaaa70000,0xa23eab64,0x2bd929a8,0xa872261f,0xabd90000,0x2aa7a61f,0xa87229a8,0x223eab64,0xabd90000,0x2aa7261f,0xa872a9a8,0x223e2b64,
0xaaa70000,0xa23e2b64,0x2bd9a9a8,0xa872a61f,0xa8720000,0xabd92b64,0xa23e29a8,0x2aa7a61f,0xa23e0000,0xa872261f,0xaaa729a8,0xabd92b64,
0x2bd92c00,0x2aa72b64,0x287229a8,0x223e261f,0x2aa72c00,0xa23e261f,0xabd9a9a8,0xa872ab64,0x28722c00,0xabd9a61f,0x223ea9a8,0x2aa72b64,
0x223e2c00,0xa872ab64,0x2aa729a8,0xabd9a61f,0xa23e2c00,0x2872ab64,0xaaa729a8,0x2bd9a61f,0xa8722c00,0x2bd9a61f,0xa23ea9a8,0xaaa72b64,
0xaaa72c00,0x223e261f,0x2bd9a9a8,0x2872ab64,0xabd92c00,0xaaa72b64,0xa87229a8,0xa23e261f,0x223e0000,0x2872a61f,0x2aa7a9a8,0x2bd9ab64,
0x28720000,0x2bd9ab64,0x223ea9a8,0xaaa7261f,0x2aa70000,0x223eab64,0xabd929a8,0x2872261f,0x2bd90000,0xaaa7a61f,0x287229a8,0xa23eab64,
0x2bd90000,0xaaa7261f,0x2872a9a8,0xa23e2b64,0x2aa70000,0x223e2b64,0xabd9a9a8,0x2872a61f,0x28720000,0x2bd92b64,0x223e29a8,0xaaa7a61f,
0x223e0000,0x2872261f,0x2aa729a8,0x2bd92b64,0xabd92c00,0xaaa72b64,0xa87229a8,0xa23e261f,0xaaa72c00,0x223e261f,0x2bd9a9a8,0x2872ab64,
0xa8722c00,0x2bd9a61f,0xa23ea9a8,0xaaa72b64,0xa23e2c00,0x2872ab64,0xaaa729a8,0x2bd9a61f,0x223e2c00,0xa872ab64,0x2aa729a8,0xabd9a61f,
0x28722c00,0xabd9a61f,0x223ea9a8,0x2aa72b64,0x2aa72c00,0xa23e261f,0xabd9a9a8,0xa872ab64,0x2bd92c00,0x2aa72b64,0x287229a8,0x223e261f,
0xa23e0000,0xa872a61f,0xaaa7a9a8,0xabd9ab64,0x28720000,0x2bd92b64,0x223e29a8,0xaaa7a61f,0xaaa70000,0xa23eab64,0x2bd929a8,0xa872261f,
0x2bd90000,0xaaa7261f,0x2872a9a8,0xa23e2b64,0xabd90000,0x2aa7261f,0xa872a9a8,0x223e2b64,0x2aa70000,0x223eab64,0xabd929a8,0x2872261f,
0xa8720000,0xabd92b64,0xa23e29a8,0x2aa7a61f,0x223e0000,0x2872a61f,0x2aa7a9a8,0x2bd9ab64,0x2bd92c00,0x2aa72b64,0x287229a8,0x223e261f,
0xaaa7ac00,0x223ea61f,0x2bd929a8,0x28722b64,0x28722c00,0xabd9a61f,0x223ea9a8,0x2aa72b64,0xa23eac00,0x28722b64,0xaaa7a9a8,0x2bd9261f,
0xa23e2c00,0x2872ab64,0xaaa729a8,0x2bd9a61f,0x2872ac00,0xabd9261f,0x223e29a8,0x2aa7ab64,0xaaa72c00,0x223e261f,0x2bd9a9a8,0x2872ab64,
0x2bd9ac00,0x2aa7ab64,0x2872a9a8,0x223ea61f,0x223e0000,0x2872a61f,0x2aa7a9a8,0x2bd9ab64,0xa8720000,0xabd92b64,0xa23e29a8,0x2aa7a61f,
0x2aa70000,0x223eab64,0xabd929a8,0x2872261f,0xabd90000,0x2aa7261f,0xa872a9a8,0x223e2b64,0x2bd90000,0xaaa7261f,0x2872a9a8,0xa23e2b64,
0xaaa70000,0xa23eab64,0x2bd929a8,0xa872261f,0x28720000,0x2bd92b64,0x223e29a8,0xaaa7a61f,0xa23e0000,0xa872a61f,0xaaa7a9a8,0xabd9ab64,
0xabd92c00,0xaaa72b64,0xa87229a8,0xa23e261f,0x2aa7ac00,0xa23ea61f,0xabd929a8,0xa8722b64,0xa8722c00,0x2bd9a61f,0xa23ea9a8,0xaaa72b64,
0x223eac00,0xa8722b64,0x2aa7a9a8,0xabd9261f,0x223e2c00,0xa872ab64,0x2aa729a8,0xabd9a61f,0xa872ac00,0x2bd9261f,0xa23e29a8,0xaaa7ab64,
0x2aa72c00,0xa23e261f,0xabd9a9a8,0xa872ab64,0xabd9ac00,0xaaa7ab64,0xa872a9a8,0xa23ea61f,0xabd9ac00,0xaaa7ab64,0xa872a9a8,0xa23ea61f,
0x2aa72c00,0xa23e261f,0xabd9a9a8,0xa872ab64,0xa872ac00,0x2bd9261f,0xa23e29a8,0xaaa7ab64,0x223e2c00,0xa872ab64,0x2aa729a8,0xabd9a61f,
0x223eac00,0xa8722b64,0x2aa7a9a8,0xabd9261f,0xa8722c00,0x2bd9a61f,0xa23ea9a8,0xaaa72b64,0x2aa7ac00,0xa23ea61f,0xabd929a8,0xa8722b64,
0xabd92c00,0xaaa72b64,0xa87229a8,0xa23e261f,0xa23e0000,0xa872a61f,0xaaa7a9a8,0xabd9ab64,0x28720000,0x2bd92b64,0x223e29a8,0xaaa7a61f,
0xaaa70000,0xa23eab64,0x2bd929a8,0xa872261f,0x2bd90000,0xaaa7261f,0x2872a9a8,0xa23e2b64,0xabd90000,0x2aa7261f,0xa872a9a8,0x223e2b64,
0x2aa70000,0x223eab64,0xabd929a8,0x2872261f,0xa8720000,0xabd92b64,0xa23e29a8,0x2aa7a61f,0x223e0000,0x2872a61f,0x2aa7a9a8,0x2bd9ab64,
0x2bd9ac00,0x2aa7ab64,0x2872a9a8,0x223ea61f,0xaaa72c00,0x223e261f,0x2bd9a9a8,0x2872ab64,0x2872ac00,0xabd9261f,0x223e29a8,0x2aa7ab64,
0xa23e2c00,0x2872ab64,0xaaa729a8,0x2bd9a61f,0xa23eac00,0x28722b64,0xaaa7a9a8,0x2bd9261f,0x28722c00,0xabd9a61f,0x223ea9a8,0x2aa72b64,
0xaaa7ac00,0x223ea61f,0x2bd929a8,0x28722b64,0x2bd92c00,0x2aa72b64,0x287229a8,0x223e261f,0x223e0000,0x2872a61f,0x2aa7a9a8,0x2bd9ab64,
0xa8720000,0xabd92b64,0xa23e29a8,0x2aa7a61f,0x2aa70000,0x223eab64,0xabd929a8,0x2872261f,0xabd90000,0x2aa7261f,0xa872a9a8,0x223e2b64,
0x2bd90000,0xaaa7261f,0x2872a9a8,0xa23e2b64,0xaaa70000,0xa23eab64,0x2bd929a8,0xa872261f,0x28720000,0x2bd92b64,0x223e29a8,0xaaa7a61f,
0xa23e0000,0xa872a61f,0xaaa7a9a8,0xabd9ab64,0x27fe2800,0x96480000,0x273b2764,0xa2d7a21f,0x27ea27f6,0x9cb29a46,0x26dd270e,0xa41da38b,
0x27c327d9,0x9fc69e3e,0x266d26a7,0xa4c4a472,0x278827a8,0xa164a0a5,0x25ed262f,0xa55fa513,0x27c32800,0x9fc60000,0xa4c4a21f,0xa66da764,
0x25ed270e,0xa55fa38b,0xa73ba62f,0xa2d7a513,0x21642472,0xa788a6a7,0xa7fea7d9,0x16489e3e,0x9cb21a46,0xa7eaa7f6,0xa6dda7a8,0x241d20a5,
0x273b2800,0xa2d70000,0xa55fa764,0x25ed221f,0x1fc62513,0xa7c3a62f,0x1cb2a0a5,0x27ea27a8,0xa4c49e3e,0xa66da7d9,0x26dd2472,0x241d26a7,
0xa7fea70e,0x9648a38b,0x278827f6,0xa1641a46,0x266d2800,0xa4c40000,0x26dd221f,0x241d2764,0xa16420a5,0xa788a7a8,0x25ed27f6,0xa55f9a46,
0xa7fea6a7,0x1648a472,0xa2d71e3e,0xa73ba7d9,0x9fc6a62f,0x27c32513,0xa7eaa70e,0x1cb2a38b,0x255f2800,0xa5ed0000,0x21642764,0xa788a21f,
0xa66d9a46,0xa4c4a7f6,0xa7c3a38b,0x9fc6a70e,0xa41da7d9,0x26dd1e3e,0x9cb2a6a7,0x27ea2472,0x273b20a5,0x22d727a8,0x27fe2513,0x1648262f,
0x241d2800,0xa6dd0000,0xa7eaa21f,0x9cb2a764,0xa7fea38b,0x9648a70e,0x2164a513,0x2788262f,0x22d7a472,0x273b26a7,0x255f27d9,0xa5ed1e3e,
0x24c427f6,0xa66d1a46,0xa7c3a0a5,0x9fc6a7a8,0x21642800,0xa7880000,0x1648a764,0x27fe221f,0xa6dda62f,0x241da513,0x24c427a8,0xa66d20a5,
0x27ea1e3e,0x1cb227d9,0xa7c3a472,0x1fc6a6a7,0xa55f238b,0xa5eda70e,0x273b9a46,0x22d727f6,0x1cb22800,0xa7ea0000,0x27c3221f,0x9fc62764,
0xa2d7a7a8,0x273ba0a5,0xa7fe9a46,0x9648a7f6,0x255f26a7,0xa5ed2472,0x27889e3e,0x216427d9,0xa6dda513,0x241da62f,0xa66d238b,0xa4c4a70e,
0x96482800,0xa7fe0000,0xa2d72764,0xa73ba21f,0x1cb2a7f6,0x27ea1a46,0x241da70e,0x26dd238b,0x9fc627d9,0xa7c39e3e,0xa4c426a7,0xa66da472,
0x2164a7a8,0x278820a5,0x255fa62f,0x25ed2513,0x9fc62800,0xa7c30000,0xa66da21f,0x24c4a764,0x255fa70e,0x25ed238b,0x22d7262f,0xa73b2513,
0xa7882472,0xa164a6a7,0x1648a7d9,0x27fe9e3e,0x27ea9a46,0x9cb227f6,0xa41d27a8,0xa6dda0a5,0xa2d72800,0xa73b0000,0x25eda764,0x255f221f,
0x27c3a513,0x1fc6262f,0xa7ea20a5,0x1cb2a7a8,0xa66d9e3e,0x24c4a7d9,0x241d2472,0xa6dd26a7,0x1648270e,0xa7fe238b,0x2164a7f6,0x27889a46,
0xa4c42800,0xa66d0000,0x241d221f,0xa6dd2764,0x2788a0a5,0xa16427a8,0x255fa7f6,0x25ed1a46,0x1648a6a7,0x27fea472,0xa73b1e3e,0x22d7a7d9,
0xa7c3262f,0x9fc6a513,0x9cb2270e,0xa7ea238b,0xa5ed2800,0xa55f0000,0xa7882764,0xa164a21f,0x24c41a46,0xa66d27f6,0x1fc6238b,0xa7c3270e,
0x26dda7d9,0x241d1e3e,0x27eaa6a7,0x1cb22472,0xa2d7a0a5,0x273ba7a8,0x9648a513,0x27fea62f,0xa6dd2800,0xa41d0000,0x9cb2a21f,0x27eaa764,
0x1648238b,0xa7fe270e,0xa7882513,0x2164a62f,0x273ba472,0xa2d726a7,0xa5ed27d9,0xa55f1e3e,0x266da7f6,0x24c49a46,0x1fc620a5,0xa7c327a8,
0xa7882800,0xa1640000,0x27fea764,0x9648221f,0xa41d262f,0xa6dd2513,0x266da7a8,0x24c4a0a5,0x1cb21e3e,0xa7ea27d9,0x1fc6a472,0x27c3a6a7,
0x25eda38b,0xa55f270e,0xa2d71a46,0x273ba7f6,0xa7ea2800,0x9cb20000,0x9fc6221f,0xa7c32764,0xa73b27a8,0xa2d720a5,0x16481a46,0xa7fe27f6,
0xa5ed26a7,0xa55f2472,0x21649e3e,0xa78827d9,0xa41d2513,0xa6dd262f,0x24c4a38b,0xa66d270e,0xa7fe2800,0x16480000,0xa73b2764,0x22d7a21f,
0xa7ea27f6,0x1cb29a46,0xa6dd270e,0x241da38b,0xa7c327d9,0x1fc69e3e,0xa66d26a7,0x24c4a472,0xa78827a8,0x2164a0a5,0xa5ed262f,0x255fa513,
0xa7c32800,0x1fc60000,0x24c4a21f,0x266da764,0xa5ed270e,0x255fa38b,0x273ba62f,0x22d7a513,0xa1642472,0x2788a6a7,0x27fea7d9,0x96489e3e,
0x1cb21a46,0x27eaa7f6,0x26dda7a8,0xa41d20a5,0xa73b2800,0x22d70000,0x255fa764,0xa5ed221f,0x9fc62513,0x27c3a62f,0x9cb2a0a5,0xa7ea27a8,
0x24c49e3e,0x266da7d9,0xa6dd2472,0xa41d26a7,0x27fea70e,0x1648a38b,0xa78827f6,0x21641a46,0xa66d2800,0x24c40000,0xa6dd221f,0xa41d2764,
0x216420a5,0x2788a7a8,0xa5ed27f6,0x255f9a46,0x27fea6a7,0x9648a472,0x22d71e3e,0x273ba7d9,0x1fc6a62f,0xa7c32513,0x27eaa70e,0x9cb2a38b,
0xa55f2800,0x25ed0000,0xa1642764,0x2788a21f,0x266d9a46,0x24c4a7f6,0x27c3a38b,0x1fc6a70e,0x241da7d9,0xa6dd1e3e,0x1cb2a6a7,0xa7ea2472,
0xa73b20a5,0xa2d727a8,0xa7fe2513,0x9648262f,0xa41d2800,0x26dd0000,0x27eaa21f,0x1cb2a764,0x27fea38b,0x1648a70e,0xa164a513,0xa788262f,
0xa2d7a472,0xa73b26a7,0xa55f27d9,0x25ed1e3e,0xa4c427f6,0x266d1a46,0x27c3a0a5,0x1fc6a7a8,0xa1642800,0x27880000,0x9648a764,0xa7fe221f,
0x26dda62f,0xa41da513,0xa4c427a8,0x266d20a5,0xa7ea1e3e,0x9cb227d9,0x27c3a472,0x9fc6a6a7,0x255f238b,0x25eda70e,0xa73b9a46,0xa2d727f6,
0x9cb22800,0x27ea0000,0xa7c3221f,0x1fc62764,0x22d7a7a8,0xa73ba0a5,0x27fe9a46,0x1648a7f6,0xa55f26a7,0x25ed2472,0xa7889e3e,0xa16427d9,
0x26dda513,0xa41da62f,0x266d238b,0x24c4a70e,0x16482800,0x27fe0000,0x22d72764,0x273ba21f,0x9cb2a7f6,0xa7ea1a46,0xa41da70e,0xa6dd238b,
0x1fc627d9,0x27c39e3e,0x24c426a7,0x266da472,0xa164a7a8,0xa78820a5,0xa55fa62f,0xa5ed2513,0x1fc62800,0x27c30000,0x266da21f,0xa4c4a764,
0xa55fa70e,0xa5ed238b,0xa2d7262f,0x273b2513,0x27882472,0x2164a6a7,0x9648a7d9,0xa7fe9e3e,0xa7ea9a46,0x1cb227f6,0x241d27a8,0x26dda0a5,
0x22d72800,0x273b0000,0xa5eda764,0xa55f221f,0xa7c3a513,0x9fc6262f,0x27ea20a5,0x9cb2a7a8,0x266d9e3e,0xa4c4a7d9,0xa41d2472,0x26dd26a7,
0x9648270e,0x27fe238b,0xa164a7f6,0xa7889a46,0x24c42800,0x266d0000,0xa41d221f,0x26dd2764,0xa788a0a5,0x216427a8,0xa55fa7f6,0xa5ed1a46,
0x9648a6a7,0xa7fea472,0x273b1e3e,0xa2d7a7d9,0x27c3262f,0x1fc6a513,0x1cb2270e,0x27ea238b,0x25ed2800,0x255f0000,0x27882764,0x2164a21f,
0xa4c41a46,0x266d27f6,0x9fc6238b,0x27c3270e,0xa6dda7d9,0xa41d1e3e,0xa7eaa6a7,0x9cb22472,0x22d7a0a5,0xa73ba7a8,0x1648a513,0xa7fea62f,
0x26dd2800,0x241d0000,0x1cb2a21f,0xa7eaa764,0x9648238b,0x27fe270e,0x27882513,0xa164a62f,0xa73ba472,0x22d726a7,0x25ed27d9,0x255f1e3e,
0xa66da7f6,0xa4c49a46,0x9fc620a5,0x27c327a8,0x27882800,0x21640000,0xa7fea764,0x1648221f,0x241d262f,0x26dd2513,0xa66da7a8,0xa4c4a0a5,
0x9cb21e3e,0x27ea27d9,0x9fc6a472,0xa7c3a6a7,0xa5eda38b,0x255f270e,0x22d71a46,0xa73ba7f6,0x27ea2800,0x1cb20000,0x1fc6221f,0x27c32764,
0x273b27a8,0x22d720a5,0x96481a46,0x27fe27f6,0x25ed26a7,0x255f2472,0xa1649e3e,0x278827d9,0x241d2513,0x26dd262f,0xa4c4a38b,0x266d270e,
0x255f25a8,0xa5eda5a8,0x2164221f,0xa788a764,0x24c42513,0xa66da62f,0x1fc620a5,0xa7c3a7a8,0x241d2472,0xa6dda6a7,0x1cb21e3e,0xa7eaa7d9,
0x22d7238b,0xa73ba70e,0x16481a46,0xa7fea7f6,0xa41da5a8,0x26dd25a8,0x27ea2764,0x1cb2221f,0x9648a0a5,0x27fe27a8,0x278827f6,0xa1649a46,
0x22d71e3e,0x273b27d9,0x255f26a7,0xa5eda472,0x266d2513,0x24c4262f,0x1fc6238b,0xa7c3a70e,0x216425a8,0xa788a5a8,0x1648a21f,0x27fe2764,
0xa41d9a46,0xa6dda7f6,0x266d238b,0x24c4270e,0xa7eaa6a7,0x9cb2a472,0x27c327d9,0x9fc61e3e,0xa5eda7a8,0x255f20a5,0x22d7262f,0xa73ba513,
0x9cb2a5a8,0x27ea25a8,0xa7c3a764,0x1fc6a21f,0x273b238b,0x22d7270e,0x9648a513,0x27fe262f,0x255f27d9,0xa5ed9e3e,0x27882472,0x216426a7,
0xa41d1a46,0xa6dda7f6,0x24c427a8,0xa66da0a5,0x964825a8,0xa7fea5a8,0xa2d7221f,0xa73ba764,0xa7eaa62f,0x1cb2a513,0xa6dda7a8,0x241da0a5,
0x1fc6a472,0x27c326a7,0x24c49e3e,0x266d27d9,0x2788270e,0xa164238b,0x25ed27f6,0xa55f1a46,0x1fc6a5a8,0x27c325a8,0x266d2764,0xa4c4221f,
0x25ed27a8,0xa55f20a5,0xa73b9a46,0xa2d7a7f6,0xa7889e3e,0xa164a7d9,0x1648a6a7,0x27fe2472,0x1cb2a62f,0x27ea2513,0x26dd270e,0xa41d238b,
0xa2d725a8,0xa73ba5a8,0x25eda21f,0x255f2764,0x9fc6a7f6,0x27c31a46,0x9cb2270e,0xa7eaa38b,0x266d26a7,0xa4c42472,0xa41da7d9,0x26dd9e3e,
0xa7fea0a5,0x9648a7a8,0x27882513,0xa164262f,0x24c4a5a8,0x266d25a8,0xa41da764,0x26dda21f,0xa164270e,0xa788a38b,0x25ed262f,0xa55f2513,
0x1648a7d9,0x27fe1e3e,0xa73ba472,0x22d7a6a7,0x1fc627f6,0xa7c31a46,0x27ea20a5,0x9cb227a8,0xa5ed25a8,0xa55fa5a8,0xa788221f,0xa164a764,
0x266da513,0x24c4262f,0x27c3a0a5,0x1fc627a8,0xa6dd2472,0xa41da6a7,0xa7ea1e3e,0x9cb2a7d9,0x273ba38b,0x22d7270e,0x27fe9a46,0x164827f6,
0x26dda5a8,0x241d25a8,0x1cb22764,0xa7ea221f,0xa7fe20a5,0x9648a7a8,0x2164a7f6,0x27881a46,0x273b1e3e,0xa2d727d9,0xa5ed26a7,0xa55fa472,
0xa4c4a513,0x266da62f,0x27c3a38b,0x1fc6270e,0xa78825a8,0xa164a5a8,0x27fea21f,0x96482764,0x26dd1a46,0xa41d27f6,0xa4c4a38b,0x266da70e,
0x9cb2a6a7,0x27eaa472,0x9fc627d9,0xa7c31e3e,0xa55f27a8,0xa5eda0a5,0x273ba62f,0x22d72513,0x27eaa5a8,0x1cb225a8,0x1fc6a764,0x27c3a21f,
0xa2d7a38b,0x273ba70e,0xa7fe2513,0x9648a62f,0xa5ed27d9,0xa55f9e3e,0x21642472,0xa78826a7,0x26dd9a46,0xa41d27f6,0x266da7a8,0x24c420a5,
0xa7fe25a8,0x1648a5a8,0xa73b221f,0x22d7a764,0x9cb2262f,0xa7ea2513,0xa41d27a8,0xa6dd20a5,0x27c3a472,0x9fc626a7,0x266d9e3e,0xa4c427d9,
0x2164a70e,0x2788a38b,0x255fa7f6,0x25ed9a46,0x27c3a5a8,0x9fc625a8,0xa4c42764,0xa66d221f,0x255fa7a8,0x25eda0a5,0x22d71a46,0xa73b27f6,
0xa1649e3e,0x2788a7d9,0x27fea6a7,0x96482472,0xa7ea262f,0x1cb2a513,0x241da70e,0x26dda38b,0xa73b25a8,0x22d7a5a8,0x255fa21f,0xa5ed2764,
0xa7c327f6,0x9fc69a46,0x27eaa70e,0x9cb2238b,0xa4c426a7,0xa66d2472,0x26dda7d9,0x241d9e3e,0x164820a5,0xa7fe27a8,0x2164a513,0x2788a62f,
0x266da5a8,0xa4c425a8,0x26dda764,0x241da21f,0x2788a70e,0xa164238b,0x255fa62f,0x25eda513,0x27fea7d9,0x96481e3e,0x22d7a472,0x273ba6a7,
0x27c3a7f6,0x1fc69a46,0x1cb2a0a5,0x27eaa7a8,0xa55f25a8,0x25eda5a8,0xa164221f,0x2788a764,0xa4c42513,0x266da62f,0x9fc620a5,0x27c3a7a8,
0xa41d2472,0x26dda6a7,0x9cb21e3e,0x27eaa7d9,0xa2d7238b,0x273ba70e,0x96481a46,0x27fea7f6,0x241da5a8,0xa6dd25a8,0xa7ea2764,0x9cb2221f,
0x1648a0a5,0xa7fe27a8,0xa78827f6,0x21649a46,0xa2d71e3e,0xa73b27d9,0xa55f26a7,0x25eda472,0xa66d2513,0xa4c4262f,0x9fc6238b,0x27c3a70e,
0xa16425a8,0x2788a5a8,0x9648a21f,0xa7fe2764,0x241d9a46,0x26dda7f6,0xa66d238b,0xa4c4270e,0x27eaa6a7,0x1cb2a472,0xa7c327d9,0x1fc61e3e,
0x25eda7a8,0xa55f20a5,0xa2d7262f,0x273ba513,0x1cb2a5a8,0xa7ea25a8,0x27c3a764,0x9fc6a21f,0xa73b238b,0xa2d7270e,0x1648a513,0xa7fe262f,
0xa55f27d9,0x25ed9e3e,0xa7882472,0xa16426a7,0x241d1a46,0x26dda7f6,0xa4c427a8,0x266da0a5,0x164825a8,0x27fea5a8,0x22d7221f,0x273ba764,
0x27eaa62f,0x9cb2a513,0x26dda7a8,0xa41da0a5,0x9fc6a472,0xa7c326a7,0xa4c49e3e,0xa66d27d9,0xa788270e,0x2164238b,0xa5ed27f6,0x255f1a46,
0x9fc6a5a8,0xa7c325a8,0xa66d2764,0x24c4221f,0xa5ed27a8,0x255f20a5,0x273b9a46,0x22d7a7f6,0x27889e3e,0x2164a7d9,0x9648a6a7,0xa7fe2472,
0x9cb2a62f,0xa7ea2513,0xa6dd270e,0x241d238b,0x22d725a8,0x273ba5a8,0xa5eda21f,0xa55f2764,0x1fc6a7f6,0xa7c31a46,0x1cb2270e,0x27eaa38b,
0xa66d26a7,0x24c42472,0x241da7d9,0xa6dd9e3e,0x27fea0a5,0x1648a7a8,0xa7882513,0x2164262f,0xa4c4a5a8,0xa66d25a8,0x241da764,0xa6dda21f,
0x2164270e,0x2788a38b,0xa5ed262f,0x255f2513,0x9648a7d9,0xa7fe1e3e,0x273ba472,0xa2d7a6a7,0x9fc627f6,0x27c31a46,0xa7ea20a5,0x1cb227a8,
0x25ed25a8,0x255fa5a8,0x2788221f,0x2164a764,0xa66da513,0xa4c4262f,0xa7c3a0a5,0x9fc627a8,0x26dd2472,0x241da6a7,0x27ea1e3e,0x1cb2a7d9,
0xa73ba38b,0xa2d7270e,0xa7fe9a46,0x964827f6,0xa6dda5a8,0xa41d25a8,0x9cb22764,0x27ea221f,0x27fe20a5,0x1648a7a8,0xa164a7f6,0xa7881a46,
0xa73b1e3e,0x22d727d9,0x25ed26a7,0x255fa472,0x24c4a513,0xa66da62f,0xa7c3a38b,0x9fc6270e,0x278825a8,0x2164a5a8,0xa7fea21f,0x16482764,
0xa6dd1a46,0x241d27f6,0x24c4a38b,0xa66da70e,0x1cb2a6a7,0xa7eaa472,0x1fc627d9,0x27c31e3e,0x255f27a8,0x25eda0a5,0xa73ba62f,0xa2d72513,
0xa7eaa5a8,0x9cb225a8,0x9fc6a764,0xa7c3a21f,0x22d7a38b,0xa73ba70e,0x27fe2513,0x1648a62f,0x25ed27d9,0x255f9e3e,0xa1642472,0x278826a7,
0xa6dd9a46,0x241d27f6,0xa66da7a8,0xa4c420a5,0x27fe25a8,0x9648a5a8,0x273b221f,0xa2d7a764,0x1cb2262f,0x27ea2513,0x241d27a8,0x26dd20a5,
0xa7c3a472,0x1fc626a7,0xa66d9e3e,0x24c427d9,0xa164a70e,0xa788a38b,0xa55fa7f6,0xa5ed9a46,0xa7c3a5a8,0x1fc625a8,0x24c42764,0x266d221f,
0xa55fa7a8,0xa5eda0a5,0xa2d71a46,0x273b27f6,0x21649e3e,0xa788a7d9,0xa7fea6a7,0x16482472,0x27ea262f,0x9cb2a513,0xa41da70e,0xa6dda38b,
0x273b25a8,0xa2d7a5a8,0xa55fa21f,0x25ed2764,0x27c327f6,0x1fc69a46,0xa7eaa70e,0x1cb2238b,0x24c426a7,0x266d2472,0xa6dda7d9,0xa41d9e3e,
0x964820a5,0x27fe27a8,0xa164a513,0xa788a62f,0xa66da5a8,0x24c425a8,0xa6dda764,0xa41da21f,0xa788a70e,0x2164238b,0xa55fa62f,0xa5eda513,
0xa7fea7d9,0x16481e3e,0xa2d7a472,0xa73ba6a7,0xa7c3a7f6,0x9fc69a46,0x9cb2a0a5,0xa7eaa7a8,
};

#define PROF(slot) do {} while (0)
#define PROF3(slot) do {} while (0)
#define PROF2(slot) do {} while (0)

__device__ __forceinline__ uint32_t smem_u32(const void* p) { return (uint32_t)__cvta_generic_to_shared(p); }

__device__ __forceinline__ void mbar_init(uint32_t a, uint32_t c) {
  asm volatile("mbarrier.init.shared::cta.b64 [%0], %1;\n" ::"r"(a), "r"(c) : "memory");
}
__device__ __forceinline__ void mbar_expect_tx(uint32_t a, uint32_t bytes) {
  asm volatile("mbarrier.arrive.expect_tx.shared::cta.b64 _, [%0], %1;\n" ::"r"(a), "r"(bytes) : "memory");
}
__device__ __forceinline__ void mbar_arrive_cluster(uint32_t cluster_addr) {
  asm volatile("mbarrier.arrive.shared::cluster.b64 _, [%0];\n" ::"r"(cluster_addr) : "memory");
}
__device__ __forceinline__ void mbar_arrive_cluster_n(uint32_t cluster_addr, uint32_t n) {
  asm volatile("mbarrier.arrive.shared::cluster.b64 _, [%0], %1;\n" ::"r"(cluster_addr), "r"(n) : "memory");
}
__device__ __forceinline__ bool mbar_try(uint32_t a, uint32_t parity) {
  uint32_t ok;
  asm volatile("{\n.reg .pred p;\nmbarrier.try_wait.parity.shared::cta.b64 p, [%1], %2;\nselp.u32 %0, 1, 0, p;\n}\n"
               : "=r"(ok) : "r"(a), "r"(parity) : "memory");
  return ok;
}
__device__ __forceinline__ void mbar_wait(uint32_t a, uint32_t parity) {
  if (mbar_try(a, parity)) return;
#pragma unroll 1
  for (int n = 0; n < SPIN_LIMIT; n++)
    if (mbar_try(a, parity)) break;
}
__device__ __forceinline__ void mbar_wait_idle(uint32_t a, uint32_t parity) {
#pragma unroll 1
  for (int n = 0; n < SPIN_LIMIT; n++) {
    uint32_t ok;
    asm volatile("{\n.reg .pred p;\nmbarrier.try_wait.parity.shared::cta.b64 p, [%1], %2, %3;\nselp.u32 %0, 1, 0, p;\n}\n"
                 : "=r"(ok) : "r"(a), "r"(parity), "r"(4000) : "memory");
    if (ok) break;
  }
}
__device__ __forceinline__ bool elect_one() {
  uint32_t p;
  asm volatile("{\n.reg .pred P;\nelect.sync _|P, 0xffffffff;\nselp.u32 %0, 1, 0, P;\n}\n" : "=r"(p));
  return p;
}
__device__ __forceinline__ uint32_t mapa(uint32_t a, uint32_t rank) {
  uint32_t r;
  asm volatile("mapa.shared::cluster.u32 %0, %1, %2;\n" : "=r"(r) : "r"(a), "r"(rank));
  return r;
}
__device__ __forceinline__ void nb_sync(int id, int n) { asm volatile("bar.sync %0, %1;\n" ::"r"(id), "r"(n) : "memory"); }
__device__ __forceinline__ void nb_arrive(int id, int n) { asm volatile("bar.arrive %0, %1;\n" ::"r"(id), "r"(n) : "memory"); }
__device__ __forceinline__ void cluster_sync_all() {
  asm volatile("barrier.cluster.arrive.relaxed.aligned;\nbarrier.cluster.wait.aligned;\n" ::: "memory");
}
__device__ __forceinline__ void fence_async_smem() { asm volatile("fence.proxy.async.shared::cta;\n" ::: "memory"); }
__device__ __forceinline__ void fence_async_all() { asm volatile("fence.proxy.async.global;\n" ::: "memory"); }

__device__ __forceinline__ void tma_load_3d(uint32_t dst, const CUtensorMap* tm, uint32_t bar, int c0, int c1, int c2) {
  asm volatile(
      "cp.async.bulk.tensor.3d.shared::cluster.global.mbarrier::complete_tx::bytes [%0], [%1, {%3, %4, %5}], [%2];\n"
      ::"r"(dst), "l"(tm), "r"(bar), "r"(c0), "r"(c1), "r"(c2) : "memory");
}
__device__ __forceinline__ void tma_load_4d(uint32_t dst, const CUtensorMap* tm, uint32_t bar, int c0, int c1, int c2, int c3) {
  asm volatile(
      "cp.async.bulk.tensor.4d.shared::cluster.global.mbarrier::complete_tx::bytes [%0], [%1, {%3, %4, %5, %6}], [%2];\n"
      ::"r"(dst), "l"(tm), "r"(bar), "r"(c0), "r"(c1), "r"(c2), "r"(c3) : "memory");
}
__device__ __forceinline__ void tma_load_3d_mc(uint32_t dst, const CUtensorMap* tm, uint32_t bar, int c0, int c1, int c2) {
  asm volatile(
      "cp.async.bulk.tensor.3d.shared::cluster.global.mbarrier::complete_tx::bytes.multicast::cluster [%0], [%1, {%3, %4, %5}], [%2], %6;\n"
      ::"r"(dst), "l"(tm), "r"(bar), "r"(c0), "r"(c1), "r"(c2), "h"((uint16_t)3) : "memory");
}
__device__ __forceinline__ void tma_load_5d(uint32_t dst, const CUtensorMap* tm, uint32_t bar, int c0, int c4) {
  asm volatile(
      "cp.async.bulk.tensor.5d.shared::cluster.global.mbarrier::complete_tx::bytes [%0], [%1, {%3, %5, %5, %5, %4}], [%2];\n"
      ::"r"(dst), "l"(tm), "r"(bar), "r"(c0), "r"(c4), "r"(0) : "memory");
}
__device__ __forceinline__ void bulk_load(uint32_t dst, const void* src, uint32_t bytes, uint32_t bar) {
  asm volatile("cp.async.bulk.shared::cluster.global.mbarrier::complete_tx::bytes [%0], [%1], %2, [%3];\n"
               ::"r"(dst), "l"(src), "r"(bytes), "r"(bar) : "memory");
}
__device__ __forceinline__ void bulk_commit() { asm volatile("cp.async.bulk.commit_group;\n" ::: "memory"); }
__device__ __forceinline__ void bulk_wait0() { asm volatile("cp.async.bulk.wait_group 0;\n" ::: "memory"); }
__device__ __forceinline__ void prefetch_tmap(const CUtensorMap* tm) {
  asm volatile("prefetch.tensormap [%0];\n" ::"l"(tm) : "memory");
}

__device__ __forceinline__ void wg_fence() { asm volatile("wgmma.fence.sync.aligned;\n" ::: "memory"); }
__device__ __forceinline__ void wg_commit() { asm volatile("wgmma.commit_group.sync.aligned;\n" ::: "memory"); }
template <int N> __device__ __forceinline__ void wg_wait() {
  asm volatile("wgmma.wait_group.sync.aligned %0;\n" ::"n"(N) : "memory");
}
__device__ __forceinline__ uint64_t mkdesc(uint32_t addr, uint32_t lbo, uint32_t sbo, uint32_t swz) {
  return (uint64_t)((addr & 0x3FFFF) >> 4) | ((uint64_t)(lbo >> 4) << 16) | ((uint64_t)(sbo >> 4) << 32) |
         ((uint64_t)swz << 62);
}

#define R4(d, o) "+f"(d[o + 0]), "+f"(d[o + 1]), "+f"(d[o + 2]), "+f"(d[o + 3])
#define R8(d, o) R4(d, o), R4(d, o + 4)
#define R16(d, o) R8(d, o), R8(d, o + 8)
#define R32(d, o) R16(d, o), R16(d, o + 16)
#define R64(d, o) R32(d, o), R32(d, o + 32)

__device__ __forceinline__ void wgmma_n192(float (&d)[96], uint64_t da, uint64_t db, uint32_t acc) {
  asm volatile(
      "{\n.reg .pred p;\nsetp.ne.u32 p, %98, 0;\n"
      "wgmma.mma_async.sync.aligned.m64n192k16.f32.bf16.bf16 "
      "{%0,%1,%2,%3,%4,%5,%6,%7,%8,%9,%10,%11,%12,%13,%14,%15,%16,%17,%18,%19,%20,%21,%22,%23,%24,%25,%26,%27,%28,%29,%30,%31,"
      "%32,%33,%34,%35,%36,%37,%38,%39,%40,%41,%42,%43,%44,%45,%46,%47,%48,%49,%50,%51,%52,%53,%54,%55,%56,%57,%58,%59,%60,%61,%62,%63,"
      "%64,%65,%66,%67,%68,%69,%70,%71,%72,%73,%74,%75,%76,%77,%78,%79,%80,%81,%82,%83,%84,%85,%86,%87,%88,%89,%90,%91,%92,%93,%94,%95}, "
      "%96, %97, p, 1, 1, 0, 1;\n}\n"
      : R64(d, 0), R32(d, 64)
      : "l"(da), "l"(db), "r"(acc));
}
__device__ __forceinline__ void wgmma_n128(float (&d)[64], uint64_t da, uint64_t db, uint32_t acc) {
  asm volatile(
      "{\n.reg .pred p;\nsetp.ne.u32 p, %66, 0;\n"
      "wgmma.mma_async.sync.aligned.m64n128k16.f32.bf16.bf16 "
      "{%0,%1,%2,%3,%4,%5,%6,%7,%8,%9,%10,%11,%12,%13,%14,%15,%16,%17,%18,%19,%20,%21,%22,%23,%24,%25,%26,%27,%28,%29,%30,%31,"
      "%32,%33,%34,%35,%36,%37,%38,%39,%40,%41,%42,%43,%44,%45,%46,%47,%48,%49,%50,%51,%52,%53,%54,%55,%56,%57,%58,%59,%60,%61,%62,%63}, "
      "%64, %65, p, 1, 1, 0, 1;\n}\n"
      : R64(d, 0)
      : "l"(da), "l"(db), "r"(acc));
}
template <int N> __device__ __forceinline__ void fence_regs(float (&d)[N]) {
#pragma unroll
  for (int i = 0; i < N; i++) asm volatile("" : "+f"(d[i])::"memory");
}

__device__ __forceinline__ void mma16816(float (&d)[4], uint32_t a0, uint32_t a1, uint32_t a2, uint32_t a3, uint32_t b0,
                                         uint32_t b1) {
  asm("mma.sync.aligned.m16n8k16.row.col.f32.bf16.bf16.f32 {%0,%1,%2,%3}, {%4,%5,%6,%7}, {%8,%9}, {%0,%1,%2,%3};\n"
      : "+f"(d[0]), "+f"(d[1]), "+f"(d[2]), "+f"(d[3])
      : "r"(a0), "r"(a1), "r"(a2), "r"(a3), "r"(b0), "r"(b1));
}
__device__ __forceinline__ void mma16816_z(float (&d)[4], uint32_t a0, uint32_t a1, uint32_t a2, uint32_t a3, uint32_t b0,
                                           uint32_t b1) {
  asm("mma.sync.aligned.m16n8k16.row.col.f32.bf16.bf16.f32 {%0,%1,%2,%3}, {%4,%5,%6,%7}, {%8,%9}, {%10,%10,%10,%10};\n"
      : "=f"(d[0]), "=f"(d[1]), "=f"(d[2]), "=f"(d[3])
      : "r"(a0), "r"(a1), "r"(a2), "r"(a3), "r"(b0), "r"(b1), "f"(0.f));
}
__device__ __forceinline__ void ldsm4t(uint32_t (&r)[4], uint32_t a) {
  asm volatile("ldmatrix.sync.aligned.m8n8.x4.trans.shared.b16 {%0,%1,%2,%3}, [%4];\n"
               : "=r"(r[0]), "=r"(r[1]), "=r"(r[2]), "=r"(r[3]) : "r"(a) : "memory");
}
__device__ __forceinline__ void ldsm2t(uint32_t& r0, uint32_t& r1, uint32_t a) {
  asm volatile("ldmatrix.sync.aligned.m8n8.x2.trans.shared.b16 {%0,%1}, [%2];\n" : "=r"(r0), "=r"(r1) : "r"(a) : "memory");
}
__device__ __forceinline__ void st_async128(uint32_t a, uint32_t bar, uint32_t x, uint32_t y, uint32_t z, uint32_t w) {
  asm volatile("st.async.weak.shared::cluster.mbarrier::complete_tx::bytes.v4.b32 [%0], {%2,%3,%4,%5}, [%1];\n"
               ::"r"(a), "r"(bar), "r"(x), "r"(y), "r"(z), "r"(w) : "memory");
}
__device__ __forceinline__ void mbar_arrive(uint32_t a) {
  asm volatile("mbarrier.arrive.shared::cta.b64 _, [%0];\n" ::"r"(a) : "memory");
}
__device__ __forceinline__ void stsm4(uint32_t a, uint32_t r0, uint32_t r1, uint32_t r2, uint32_t r3) {
  asm volatile("stmatrix.sync.aligned.m8n8.x4.shared.b16 [%0], {%1,%2,%3,%4};\n"
               ::"r"(a), "r"(r0), "r"(r1), "r"(r2), "r"(r3) : "memory");
}
__device__ __forceinline__ void stsm4t(uint32_t a, uint32_t r0, uint32_t r1, uint32_t r2, uint32_t r3) {
  asm volatile("stmatrix.sync.aligned.m8n8.x4.trans.shared.b16 [%0], {%1,%2,%3,%4};\n"
               ::"r"(a), "r"(r0), "r"(r1), "r"(r2), "r"(r3) : "memory");
}
__device__ __forceinline__ uint2 lds64(uint32_t a) {
  uint2 v;
  asm volatile("ld.shared.v2.u32 {%0,%1}, [%2];\n" : "=r"(v.x), "=r"(v.y) : "r"(a));
  return v;
}
__device__ __forceinline__ uint4 lds128(uint32_t a) {
  uint4 v;
  asm volatile("ld.shared.v4.u32 {%0,%1,%2,%3}, [%4];\n" : "=r"(v.x), "=r"(v.y), "=r"(v.z), "=r"(v.w) : "r"(a) : "memory");
  return v;
}
__device__ __forceinline__ void sts128(uint32_t a, uint32_t x, uint32_t y, uint32_t z, uint32_t w) {
  asm volatile("st.shared.v4.u32 [%0], {%1,%2,%3,%4};\n" ::"r"(a), "r"(x), "r"(y), "r"(z), "r"(w) : "memory");
}
__device__ __forceinline__ uint32_t pack_bf16(float lo, float hi) {
  uint32_t r;
  asm("cvt.rn.bf16x2.f32 %0, %1, %2;\n" : "=r"(r) : "f"(hi), "f"(lo));
  return r;
}
__device__ __forceinline__ uint32_t bmul2(uint32_t a, uint32_t b) {
  uint32_t r;
  asm("mul.rn.bf16x2 %0, %1, %2;\n" : "=r"(r) : "r"(a), "r"(b));
  return r;
}
__device__ __forceinline__ uint32_t bmax2(uint32_t a, uint32_t b) {
  uint32_t r;
  asm("max.bf16x2 %0, %1, %2;\n" : "=r"(r) : "r"(a), "r"(b));
  return r;
}
__device__ __forceinline__ uint32_t bfma2(uint32_t a, uint32_t b, uint32_t c) {
  uint32_t r;
  asm("fma.rn.bf16x2 %0, %1, %2, %3;\n" : "=r"(r) : "r"(a), "r"(b), "r"(c));
  return r;
}
__device__ __forceinline__ uint32_t badd2(uint32_t a, uint32_t b) {
  uint32_t r;
  asm("add.rn.bf16x2 %0, %1, %2;\n" : "=r"(r) : "r"(a), "r"(b));
  return r;
}
__device__ __forceinline__ void prefetch_l2(const void* p) { asm volatile("prefetch.global.L2 [%0];\n" ::"l"(p)); }
__device__ __forceinline__ void cp_async16n(uint32_t dst, const void* src) {
  asm volatile("cp.async.cg.shared.global [%0], [%1], 16;\n" ::"r"(dst), "l"(src) : "memory");
}
__device__ __forceinline__ void cp_async16(uint32_t dst, const void* src, uint32_t srcbytes) {
  asm volatile("cp.async.cg.shared.global.L2::256B [%0], [%1], 16, %2;\n" ::"r"(dst), "l"(src), "r"(srcbytes) : "memory");
}
__device__ __forceinline__ uint32_t ld_acquire(const uint32_t* p) {
  uint32_t v;
  asm volatile("ld.acquire.gpu.global.u32 %0, [%1];\n" : "=r"(v) : "l"(p) : "memory");
  return v;
}
__device__ __forceinline__ uint32_t ld_relaxed(const uint32_t* p) {
  uint32_t v;
  asm volatile("ld.relaxed.gpu.global.u32 %0, [%1];\n" : "=r"(v) : "l"(p) : "memory");
  return v;
}
__device__ __forceinline__ void st_release(uint32_t* p, uint32_t v) {
  asm volatile("st.release.gpu.global.u32 [%0], %1;\n" ::"l"(p), "r"(v) : "memory");
}
__device__ __forceinline__ void wait_flag(const uint32_t* p, uint32_t want) {
  int n = 0;
  while (ld_relaxed(p) != want && ++n < SPIN_LIMIT) __nanosleep(40);
  (void)ld_acquire(p);
}

struct Params {
  const __nv_bfloat16* x;
  const __nv_bfloat16* w;
  const __nv_bfloat16* q;
  const __nv_bfloat16* k;
  const __nv_bfloat16* v;
  const __nv_bfloat16* shift_k;
  const __nv_bfloat16* ssm_k;
  const __nv_bfloat16* ssm_D;
  const __nv_bfloat16* wo;
  __nv_bfloat16* out;
};

__device__ __forceinline__ uint32_t lds32(uint32_t a) {
  uint32_t v;
  asm volatile("ld.shared.u32 %0, [%1];\n" : "=r"(v) : "r"(a));
  return v;
}
#define W4(d, o) "=f"(d[o + 0]), "=f"(d[o + 1]), "=f"(d[o + 2]), "=f"(d[o + 3])
#define W8(d, o) W4(d, o), W4(d, o + 4)
#define W16(d, o) W8(d, o), W8(d, o + 8)
#define U4(c, d, o) c(d[o + 0]), c(d[o + 1]), c(d[o + 2]), c(d[o + 3])
#define U8(c, d, o) U4(c, d, o), U4(c, d, o + 4)
#define U16(c, d, o) U8(c, d, o), U8(c, d, o + 8)
#define U32(c, d, o) U16(c, d, o), U16(c, d, o + 16)
#define D32 "{%0,%1,%2,%3,%4,%5,%6,%7,%8,%9,%10,%11,%12,%13,%14,%15,%16,%17,%18,%19,%20,%21,%22,%23,%24,%25,%26,%27,%28,%29,%30,%31}"
#define D16 "{%0,%1,%2,%3,%4,%5,%6,%7,%8,%9,%10,%11,%12,%13,%14,%15}"
#define D8 "{%0,%1,%2,%3,%4,%5,%6,%7}"
template <int ACC> __device__ __forceinline__ void hmma_n128t(uint32_t (&d)[32], const uint32_t (&a)[4], uint64_t db) {
  if (ACC)
    asm volatile("wgmma.mma_async.sync.aligned.m64n128k16.f16.f16.f16 " D32 ", {%32,%33,%34,%35}, %36, 1, 1, 1, 1;\n"
                 : U32("+r", d, 0) : "r"(a[0]), "r"(a[1]), "r"(a[2]), "r"(a[3]), "l"(db));
  else
    asm volatile("wgmma.mma_async.sync.aligned.m64n128k16.f16.f16.f16 " D32 ", {%32,%33,%34,%35}, %36, 0, 1, 1, 1;\n"
                 : U32("=r", d, 0) : "r"(a[0]), "r"(a[1]), "r"(a[2]), "r"(a[3]), "l"(db));
}
template <int ACC, int TB> __device__ __forceinline__ void hmma_n32(uint32_t (&d)[8], const uint32_t (&a)[4], uint64_t db) {
  if (ACC)
    asm volatile("wgmma.mma_async.sync.aligned.m64n32k16.f16.f16.f16 " D8 ", {%8,%9,%10,%11}, %12, 1, 1, 1, %13;\n"
                 : U8("+r", d, 0) : "r"(a[0]), "r"(a[1]), "r"(a[2]), "r"(a[3]), "l"(db), "n"(TB));
  else
    asm volatile("wgmma.mma_async.sync.aligned.m64n32k16.f16.f16.f16 " D8 ", {%8,%9,%10,%11}, %12, 0, 1, 1, %13;\n"
                 : U8("=r", d, 0) : "r"(a[0]), "r"(a[1]), "r"(a[2]), "r"(a[3]), "l"(db), "n"(TB));
}
template <int ACC> __device__ __forceinline__ void fmma_n32t(float (&d)[16], const uint32_t (&a)[4], uint64_t db) {
  if (ACC)
    asm volatile("wgmma.mma_async.sync.aligned.m64n32k16.f32.f16.f16 " D16 ", {%16,%17,%18,%19}, %20, 1, 1, 1, 1;\n"
                 : R16(d, 0) : "r"(a[0]), "r"(a[1]), "r"(a[2]), "r"(a[3]), "l"(db));
  else
    asm volatile("wgmma.mma_async.sync.aligned.m64n32k16.f32.f16.f16 " D16 ", {%16,%17,%18,%19}, %20, 0, 1, 1, 1;\n"
                 : W16(d, 0) : "r"(a[0]), "r"(a[1]), "r"(a[2]), "r"(a[3]), "l"(db));
}
template <int N> __device__ __forceinline__ void fence_regs(uint32_t (&d)[N]) {
#pragma unroll
  for (int i = 0; i < N; i++) asm volatile("" : "+r"(d[i])::"memory");
}
__device__ __forceinline__ uint32_t hmul(uint32_t a, uint32_t b) { uint32_t r; asm("mul.rn.f16x2 %0, %1, %2;\n" : "=r"(r) : "r"(a), "r"(b)); return r; }
__device__ __forceinline__ uint32_t hadd(uint32_t a, uint32_t b) { uint32_t r; asm("add.rn.f16x2 %0, %1, %2;\n" : "=r"(r) : "r"(a), "r"(b)); return r; }
__device__ __forceinline__ uint32_t hsub(uint32_t a, uint32_t b) { uint32_t r; asm("sub.rn.f16x2 %0, %1, %2;\n" : "=r"(r) : "r"(a), "r"(b)); return r; }
__device__ __forceinline__ uint32_t hfma(uint32_t a, uint32_t b, uint32_t c) { uint32_t r; asm("fma.rn.f16x2 %0, %1, %2, %3;\n" : "=r"(r) : "r"(a), "r"(b), "r"(c)); return r; }
__device__ __forceinline__ uint32_t hfnma(uint32_t a, uint32_t b, uint32_t c) {
  uint32_t r;
  asm("{\n.reg .b32 t;\nneg.f16x2 t, %1;\nfma.rn.f16x2 %0, t, %2, %3;\n}\n" : "=r"(r) : "r"(a), "r"(b), "r"(c));
  return r;
}
__device__ __forceinline__ uint32_t hrefl(uint32_t p, uint32_t s) {
  uint32_t r;
  asm("{\n.reg .b32 t;\nneg.f16x2 t, %2;\nfma.rn.f16x2 %0, %1, %3, t;\n}\n" : "=r"(r) : "r"(p), "r"(s), "r"(0x40004000u));
  return r;
}
__device__ __forceinline__ void bfly(uint32_t xr, uint32_t xi, uint32_t tr, uint32_t ti, uint32_t yr, uint32_t yi, uint32_t ur,
                                     uint32_t ui, uint32_t& sr, uint32_t& si, uint32_t& dr, uint32_t& di) {
  const uint32_t pr = hfnma(xi, ti, hmul(xr, tr)), pi = hfma(xi, tr, hmul(xr, ti));
  sr = hfnma(yi, ui, hfma(yr, ur, pr));
  si = hfma(yi, ur, hfma(yr, ui, pi));
  dr = hrefl(pr, sr);
  di = hrefl(pi, si);
}
template <int BH> __device__ __forceinline__ void fft_e1(const uint32_t (&d)[32], const uint32_t (&tw)[16], uint32_t (&a2)[2][2][4]) {
#pragma unroll
  for (int be = 0; be < 2; be++)
#pragma unroll
    for (int s = 0; s < 2; s++) {
      const int o = 16 * s + 8 * be + 2 * BH, p = 2 * BH;
      bfly(d[o], d[o + 1], tw[p], tw[p + 1], d[o + 4], d[o + 5], tw[p + 4], tw[p + 5], a2[be][0][s], a2[be][0][2 + s],
           a2[be][1][s], a2[be][1][2 + s]);
    }
}
__device__ __forceinline__ uint32_t hfms(uint32_t a, uint32_t b, uint32_t c) {
  uint32_t r;
  asm("{\n.reg .b32 t;\nneg.f16x2 t, %3;\nfma.rn.f16x2 %0, %1, %2, t;\n}\n" : "=r"(r) : "r"(a), "r"(b), "r"(c));
  return r;
}
template <int C, int J> __device__ __forceinline__ void fft_e2(const uint32_t (&d0)[8], const uint32_t (&d1)[8], uint32_t (&a3)[2][4]) {
  const uint32_t ur = d0[2 * J], ui = d0[4 + 2 * J], hr = d0[2 * J + 1], hi = d0[5 + 2 * J];
  const uint32_t vr = d1[2 * J], vi = d1[4 + 2 * J], gr = d1[2 * J + 1], gi = d1[5 + 2 * J];
  const uint32_t pr = hfnma(ui, hi, hmul(ur, hr)), pi = hfma(ui, hr, hmul(ur, hi));
  a3[0][2 + C] = pr;
  a3[0][C] = pi;
  a3[1][2 + C] = hfnma(vi, hi, hfma(vr, hr, hfnma(ui, gi, hfms(ur, gr, pi))));
  a3[1][C] = hfma(vi, hr, hfma(vr, hi, hfma(ui, gr, hfma(ur, gi, pr))));
}
__device__ __forceinline__ void fft_e3(const uint32_t (&d)[2][8], const uint32_t (&tw)[16], uint32_t zaddr) {
#pragma unroll
  for (int rho = 0; rho < 2; rho++) {
    uint32_t zr[4], zi[4];
#pragma unroll
    for (int nb = 0; nb < 4; nb++) {
      const uint32_t xi = d[nb >> 1][2 * (nb & 1) + rho], xr = d[nb >> 1][4 + 2 * (nb & 1) + rho];
      const uint32_t tr = tw[8 + 4 * rho + 2 * (nb & 1)], ti = tw[9 + 4 * rho + 2 * (nb & 1)];
      zr[nb] = hfnma(xi, ti, hmul(xr, tr));
      zi[nb] = hfma(xi, tr, hmul(xr, ti));
    }
    stsm4(zaddr + rho * 1024, zr[0], zr[1], zr[2], zr[3]);
    stsm4(zaddr + rho * 1024 + 512, zi[0], zi[1], zi[2], zi[3]);
  }
}
__device__ __forceinline__ float bf_lo(uint32_t v) {
  uint32_t r;
  asm("prmt.b32 %0, %1, 0, 0x1044;\n" : "=r"(r) : "r"(v));
  return __uint_as_float(r);
}
__device__ __forceinline__ float bf_hi(uint32_t v) { return __uint_as_float(v & 0xffff0000u); }
__device__ __forceinline__ float ex2(float x) {
  float r;
  asm("ex2.approx.ftz.f32 %0, %1;\n" : "=f"(r) : "f"(x));
  return r;
}
__device__ __forceinline__ float rcp(float x) {
  float r;
  asm("rcp.approx.ftz.f32 %0, %1;\n" : "=f"(r) : "f"(x));
  return r;
}

__device__ __forceinline__ int g2_a(int s) { return ((0xA1054 >> (4 * s)) & 15) * 16384; }
__device__ __forceinline__ int g2_b(int s) { return ((0xCDB32 >> (4 * s)) & 15) * 16384; }
static_assert(OFF_U == 10 * 16384 && OFF_H == 12 * 16384 && OFF_OP == 4 * 16384, "units");
__device__ __forceinline__ int g2_k(int hp, int i) { return i < 2 ? hp ^ 1 ^ i : i < 4 ? (hp & ~1) ^ i : ((hp & ~3) + i) & 15; }
__device__ __forceinline__ int y_slot(int wg, int it) {
  static_assert(T_B2 == T_TW + 8192 && T_A1 == T_B2 + 4096, "y slots");
  return OFF_T + T_TW + ((it + 3) & 3) * 4096 + wg * 2048;
}

__device__ __forceinline__ void to_arr(uint32_t (&d)[4], uint4 v) { d[0] = v.x; d[1] = v.y; d[2] = v.z; d[3] = v.w; }

__device__ __forceinline__ void attn_stage(uint32_t sb, int blk, int lane, const float (&acc)[96], uint32_t (&k1)[2][4]) {
  const int lr = lane & 7, lm = lane >> 3;
  const uint32_t base = sb + OFF_VP + (blk * 16 + lr + 8 * (lm & 1)) * 128;
#pragma unroll
  for (int i = 0; i < 8; i++) k1[i >> 2][i & 3] = pack_bf16(acc[34 + 4 * i], acc[35 + 4 * i]);
  const uint32_t kh = sb + OFF_KH + blk * 2048 + lane * 16;
  sts128(kh, k1[0][0], k1[0][1], k1[0][2], k1[0][3]);
  sts128(kh + 512, k1[1][0], k1[1][1], k1[1][2], k1[1][3]);
#pragma unroll
  for (int j = 0; j < 8; j += 2)
    stsm4(base + (((j + (lm >> 1)) ^ lr) << 4), pack_bf16(acc[64 + 4 * j], acc[65 + 4 * j]),
          pack_bf16(acc[66 + 4 * j], acc[67 + 4 * j]), pack_bf16(acc[68 + 4 * j], acc[69 + 4 * j]),
          pack_bf16(acc[70 + 4 * j], acc[71 + 4 * j]));
}
__device__ __forceinline__ void attn_pack(const float (&acc)[96], uint32_t (&qa)[2][8], uint32_t (&k0)[2][4]) {
#pragma unroll
  for (int hd = 0; hd < 2; hd++) {
#pragma unroll
    for (int i = 0; i < 8; i++) {
      asm volatile("cvt.rn.bf16x2.f32 %0, %1, %2;\n" : "=r"(qa[hd][i]) : "f"(acc[16 * hd + 2 * i + 1]), "f"(acc[16 * hd + 2 * i]));
    }
#pragma unroll
    for (int i = 0; i < 4; i++) {
      asm volatile("cvt.rn.bf16x2.f32 %0, %1, %2;\n" : "=r"(k0[hd][i]) : "f"(acc[33 + 16 * hd + 4 * i]), "f"(acc[32 + 16 * hd + 4 * i]));
    }
  }
}
__device__ __forceinline__ void attn_own(const uint32_t (&k0)[2][4], const uint32_t (&k1)[2][4], bool le0, bool le1,
                                         const uint32_t (&qa)[2][8], float (&l)[2][4]) {
#pragma unroll
  for (int hd = 0; hd < 2; hd++) {
    float s0[4], s1[4];
    mma16816_z(s0, qa[hd][0], qa[hd][1], qa[hd][2], qa[hd][3], k0[hd][0], k0[hd][1]);
    mma16816_z(s1, qa[hd][0], qa[hd][1], qa[hd][2], qa[hd][3], k1[hd][0], k1[hd][1]);
    mma16816(s0, qa[hd][4], qa[hd][5], qa[hd][6], qa[hd][7], k0[hd][2], k0[hd][3]);
    mma16816(s1, qa[hd][4], qa[hd][5], qa[hd][6], qa[hd][7], k1[hd][2], k1[hd][3]);
    l[hd][0] = s0[0];
    l[hd][1] = s0[1];
    l[hd][2] = le0 ? s1[2] : s0[2];
    l[hd][3] = le1 ? s1[3] : s0[3];
  }
}
template <int N> __device__ __forceinline__ void quad_softmax(float (&x)[N][2], uint32_t (&pp)[N]) {
  const float c2 = 1.4426950408889634f;
  uint32_t q[N], mx[N / 2];
#pragma unroll
  for (int n = 0; n < N; n++) {
    const uint32_t r = pack_bf16(x[n][0], x[n][1]);
    q[n] = bfma2(r, 0x3e353e35u, bmul2(r, 0x379e379eu));
    x[n][0] = bf_lo(q[n]);
    x[n][1] = bf_hi(q[n]);
  }
#pragma unroll
  for (int n = 0; n < N / 2; n++)
    mx[n] = bmax2(__byte_perm(q[2 * n], q[2 * n + 1], 0x5410), __byte_perm(q[2 * n], q[2 * n + 1], 0x7632));
#pragma unroll
  for (int o = 1; o <= 2; o++)
#pragma unroll
    for (int n = 0; n < N / 2; n++) mx[n] = bmax2(mx[n], __shfl_xor_sync(0xffffffffu, mx[n], o));
  float m[N], t[N];
#pragma unroll
  for (int n = 0; n < N / 2; n++) {
    m[2 * n] = bf_lo(mx[n]);
    m[2 * n + 1] = bf_hi(mx[n]);
  }
#pragma unroll
  for (int n = 0; n < N; n++) {
    const float nm = -m[n] * c2;
    x[n][0] = ex2(fmaf(x[n][0], c2, nm));
    x[n][1] = ex2(fmaf(x[n][1], c2, nm));
    t[n] = x[n][0] + x[n][1];
  }
#pragma unroll
  for (int o = 1; o <= 2; o++)
#pragma unroll
    for (int n = 0; n < N; n++) t[n] += __shfl_xor_sync(0xffffffffu, t[n], o);
#pragma unroll
  for (int n = 0; n < N; n++) {
    const float inv = rcp(t[n]);
    pp[n] = pack_bf16(x[n][0] * inv, x[n][1] * inv);
  }
}
__device__ __forceinline__ void attn_pv(uint32_t dst, const uint32_t (&va)[4], const uint32_t (&vb)[4], uint32_t pp,
                                        uint32_t maskLE) {
  const uint32_t b0 = pp & ~maskLE, b1 = pp & maskLE;
  float oa[4], ob[4];
  mma16816_z(oa, va[0], va[1], va[2], va[3], b0, b1);
  mma16816_z(ob, vb[0], vb[1], vb[2], vb[3], b0, b1);
  stsm4t(dst, pack_bf16(oa[0], oa[1]), pack_bf16(oa[2], oa[3]), pack_bf16(ob[0], ob[1]), pack_bf16(ob[2], ob[3]));
}

template <int MODE>
__global__ void __cluster_dims__(2, 1, 1) __launch_bounds__(NTHREADS, 1)
fused_kernel(const Params p, const __grid_constant__ CUtensorMap tmX, const __grid_constant__ CUtensorMap tmW,
             const __grid_constant__ CUtensorMap tmWo,
             const __grid_constant__ CUtensorMap tmQ,
             const __grid_constant__ CUtensorMap tmXh, const __grid_constant__ CUtensorMap tmWh) {
  extern __shared__ __align__(1024) uint8_t smem[];
  const uint32_t sb = smem_u32(smem);
  const uint32_t bars = sb + OFF_BAR;
  const int tid = threadIdx.x, lane = tid & 31, warp = __shfl_sync(0xffffffffu, tid >> 5, 0);
  const int rank = blockIdx.x & 1;
  const bool halo_cta = blockIdx.x < 4;
  if (halo_cta && MODE != 0) return;
  int grp, mem;
  {
    const int t = (blockIdx.x >> 1) - 4, u = t - 32;
    const int q7 = (u * 37) >> 8;
    const bool lo = (unsigned)t < 32u, mid = (unsigned)u < 28u;
    grp = lo ? (t & 7) : (mid ? 1 + u - 7 * q7 : 0);
    mem = lo ? (t >> 3) : (mid ? 4 + q7 : (t < 0 ? t + 6 : t - 54));
  }
  const int rg = (grp >> 2) * 4 + (mem >> 1), hp = (grp & 3) * 4 + (mem & 1) * 2 + rank;
  const int rb2 = (grp >> 2) * 8 + mem, cb2 = (grp & 3) * 2 + rank;
  const int chb = grp * 16 + mem * 2 + rank;
  const int cta = rg * 16 + hp;
  const int par = rg >> 2, gidx = rg & 3;

  if (tid < 256 && !halo_cta && MODE != 2) {
    const int r = tid >> 3, c = tid & 7;
    const uint32_t so = r * 128 + ((c ^ (r & 7)) << 4);
    const __nv_bfloat16* wg0 = p.w + (size_t)r * (3 * DM) + hp * 64 + c * 8;
    const __nv_bfloat16* xg0 = p.x + (size_t)(2 * (gidx * 256 + r) + par) * DM + c * 8;
#pragma unroll
    for (int j = 0; j < 3; j++) cp_async16n(sb + OFF_1B + j * 4096 + so, wg0 + j * DM);
#pragma unroll
    for (int i = 0; i < 8; i++) cp_async16n(sb + i * 4096 + so, xg0 + (size_t)i * 64 * DM);
    asm volatile("cp.async.commit_group;\n" ::: "memory");
  }
  if (tid == 256) {
    prefetch_tmap(halo_cta ? &tmXh : &tmX);
#pragma unroll
    for (int i = 0; i < NS1B; i++) mbar_init(bars + 8 * (BAR_FULLB + i), 1);
#pragma unroll
    for (int i = 0; i < NS1A; i++) mbar_init(bars + 8 * (BAR_FULLA + i), 1);
    asm volatile("fence.mbarrier_init.release.cluster;\n" ::: "memory");
    if (!halo_cta && MODE != 2) {
      mbar_expect_tx(bars + 8 * (BAR_FULLB + 1), STG1B);
      tma_load_3d(sb + OFF_1B + 1 * STG1B, &tmW, bars + 8 * (BAR_FULLB + 1), hp * 64, 32, 0);
      mbar_expect_tx(bars + 8 * (BAR_FULLB + 2), STG1B);
      tma_load_3d(sb + OFF_1B + 2 * STG1B, &tmW, bars + 8 * (BAR_FULLB + 2), hp * 64, 64, 0);
    } else {
      prefetch_tmap(&tmWh);
    }
  } else if (tid == 288) {
#pragma unroll
    for (int i = 0; i < NS1A; i++) mbar_init(bars + 8 * (BAR_EMPTYA + i), 4);
#pragma unroll
    for (int i = 0; i < NS1B; i++) mbar_init(bars + 8 * (BAR_EMPTYB + i), 2);
    asm volatile("fence.mbarrier_init.release.cluster;\n" ::: "memory");
  } else if (tid == 320) {
#pragma unroll
    for (int i = 0; i < NS2; i++) {
      mbar_init(bars + 8 * (BAR_FULL2 + i), 1);
      mbar_init(bars + 8 * (BAR_EMPTY2 + i), 4);
    }
    mbar_init(bars + 8 * BAR_DEAD, 2);
    mbar_init(bars + 8 * (BAR_DEAD + 1), 2);
    mbar_init(bars + 8 * BAR_X, 2);
    mbar_init(bars + 8 * BAR_REL, 2);
    asm volatile("fence.mbarrier_init.release.cluster;\n" ::: "memory");
  } else if (tid == 352) {
    mbar_init(bars + 8 * BAR_T, 1);
    mbar_init(bars + 8 * BAR_UH, 3);
    mbar_init(bars + 8 * BAR_LFREE, 4);
    mbar_init(bars + 8 * BAR_LAND, 1);
    mbar_init(bars + 8 * BAR_U, 1);
    mbar_init(bars + 8 * BAR_Q, 1);
    mbar_init(bars + 8 * BAR_STG, 9);
    asm volatile("fence.mbarrier_init.release.cluster;\n" ::: "memory");
  }
  if (warp == 8) PROF2(23);
  cluster_sync_all();
  if (warp == 8) PROF2(24);

  if (warp >= 8) {
    const int hw = warp - 8;
    const int lr = lane & 7, lm = lane >> 3;
    auto g1_issue_a = [&](int j, int s) {
      const uint32_t fb = bars + 8 * (BAR_FULLA + s);
      mbar_expect_tx(fb, STG1A);
      tma_load_3d_mc(sb + s * STG1A + rank * 16384, &tmX, fb, j * 64, par, gidx * 256 + rank * 128);
    };
    auto g1_issue_b = [&](int kb, int s) {
      const uint32_t fb = bars + 8 * (BAR_FULLB + s);
      mbar_expect_tx(fb, STG1B);
      tma_load_3d(sb + OFF_1B + s * STG1B, &tmW, fb, hp * 64, kb * 32, 0);
    };
    asm volatile("setmaxnreg.dec.sync.aligned.u32 %0;\n" :: "n"(REG_HELP));

    if (halo_cta) {
      if (hw == 0) {
        int s = 0, ph = 1;
#pragma unroll 1
        for (int kb = 0; kb < 16; kb++) {
          mbar_wait(bars + 8 * (BAR_EMPTYB + s), ph);
          const uint32_t fb = bars + 8 * (BAR_FULLB + s), st = sb + s * STGH;
          if (elect_one()) {
            mbar_expect_tx(fb, STGH);
            tma_load_4d(st, &tmXh, fb, kb * 64, 248, 0, 0);
            tma_load_3d(st + 8192, &tmWh, fb, 0, kb * 64, 16 + blockIdx.x * 4);
            tma_load_3d(st + 8192 + 32768, &tmWh, fb, 0, kb * 64, 32 + blockIdx.x * 4);
          }
          if (++s == 3) { s = 0; ph ^= 1; }
        }
      }
      __syncwarp();
    } else if (hw == 0) {
      uint32_t epoch = 0;
      if (lane < (MODE == 2 ? NS2 : 2)) mbar_arrive_cluster_n(mapa(bars, rank) + 8 * (BAR_EMPTY2 + lane), 4);
      if (MODE != 2) {
      epoch = ld_relaxed(g_flag_o + 2 * cta) + 1;
      if (lane == 0) {
        mbar_expect_tx(bars + 8 * BAR_U, 32768);
        mbar_expect_tx(bars + 8 * BAR_LAND, 32768);
        mbar_expect_tx(bars + 8 * BAR_Q, 32768);
        mbar_expect_tx(bars + 8 * BAR_T, T_END);
      }
      {
        int sa = 1, pha = 1, sbb = 2, phb = 1;
#pragma unroll 1
        for (int kb = 2; kb < 32; kb++) {
          if (!(kb & 1)) {
            mbar_wait(bars + 8 * (BAR_EMPTYA + sa), pha);
            if (elect_one()) g1_issue_a(kb >> 1, sa);
            if (++sa == NS1A) { sa = 0; pha ^= 1; }
          }
          mbar_wait(bars + 8 * (BAR_EMPTYB + sbb), phb);
          if (kb > 2 && elect_one()) g1_issue_b(kb, sbb);
          __syncwarp();
          if (kb >= PF0 && kb < PF0 + 12)
            prefetch_l2((kb < PF0 + 8 ? p.q + (size_t)chb * 16384 + (kb - PF0) * 2048 : p.wo + (size_t)chb * 8192 + (kb - PF0 - 8) * 2048) + lane * 64);
          if (kb == 4) PROF2(27);
          if (kb == 1) PROF2(38);
          if (kb == 2) PROF2(39);
          if (++sbb == NS1B) { sbb = 0; phb ^= 1; }
        }
      }
      static_assert(32 % NS1B == 2 && (32 / NS1B) % 2 == 0 && OFF_Q == OFF_1B && 2 * STG1B == 6 * 4096, "slots / parity of these loads");
      const uint8_t* tab = reinterpret_cast<const uint8_t*>(g_tab);
      if (lane == 0) {
        prefetch_tmap(&tmWo);
        prefetch_tmap(&tmQ);
        bulk_load(sb + OFF_T + T_A1, tab + T_A1, T_END - T_A1, bars + 8 * BAR_T);
        mbar_wait(bars + 8 * (BAR_EMPTYB + 2), 1);
        tma_load_5d(sb + OFF_Q + 6 * 4096, &tmQ, bars + 8 * BAR_Q, (chb & ~1) * 8, rank * 32 + 24);
        tma_load_5d(sb + OFF_Q + 7 * 4096, &tmQ, bars + 8 * BAR_Q, (chb & ~1) * 8, rank * 32 + 28);
        if (gidx != 0) wait_flag(g_flag_h + (hp >> 2), epoch);
      }
      __syncwarp();
      {
        uint4 hk0 = make_uint4(0, 0, 0, 0), hk1 = hk0, hv0 = hk0, hv1 = hk0;
        if (gidx != 0) {
          const uint4* src = g_halo + cta * 128 + lane;
          hk0 = __ldcg(src); hk1 = __ldcg(src + 32); hv0 = __ldcg(src + 64); hv1 = __ldcg(src + 96);
        }
        if (lane == 0) {
          mbar_wait(bars + 8 * (BAR_EMPTYB + 3), 1);
          bulk_load(sb + OFF_T, tab, T_TW, bars + 8 * BAR_T);
        }
        __syncwarp();
        PROF2(18);
        sts128(sb + OFF_L0 + 1024 + lane * 16, hk0.x, hk0.y, hk0.z, hk0.w);
        sts128(sb + OFF_L0 + 1536 + lane * 16, hk1.x, hk1.y, hk1.z, hk1.w);
        stsm4(sb + OFF_L0 + lr * 128 + ((lm ^ lr) << 4), hv0.x, hv0.y, hv0.z, hv0.w);
        stsm4(sb + OFF_L0 + lr * 128 + (((4 + lm) ^ lr) << 4), hv1.x, hv1.y, hv1.z, hv1.w);
        __syncwarp();
        if (lane == 0) {
          mbar_arrive(bars + 8 * BAR_STG);
          mbar_wait(bars + 8 * (BAR_EMPTYB + 4), 1);
          bulk_load(sb + OFF_T + T_TW, tab + T_TW, T_A1 - T_TW, bars + 8 * BAR_T);
          mbar_wait(bars + 8 * BAR_EMPTYB, 0);
#pragma unroll 1
          for (int i = 0; i < 6; i++) tma_load_5d(sb + OFF_Q + i * 4096, &tmQ, bars + 8 * BAR_Q, (chb & ~1) * 8, rank * 32 + i * 4);
        }
        __syncwarp();
      }
      }
      if (MODE != 1) {
        auto korder = [&](int i) { return MODE == 2 ? i : g2_k(hp, i); };
        if (MODE == 0) {
          mbar_wait_idle(bars + 8 * (BAR_EMPTY2 + 2), 0);
          if (elect_one()) {
            mbar_expect_tx(bars + 8 * BAR_FULL2, STG2);
            tma_load_3d(sb + g2_b(0), &tmWo, bars + 8 * BAR_FULL2, 0, korder(0) * 64, cb2 * 2);
            tma_load_3d(sb + g2_b(1), &tmWo, bars + 8 * (BAR_FULL2 + 1), 0, korder(1) * 64, cb2 * 2);
          }
        }
        PROF2(20);
        const __nv_bfloat16* osrc = g_o + (size_t)(rb2 >> 1) * 16 * 16384 + ((rb2 & 1) * 2 + rank) * 4096;
        const uint32_t* flag = g_flag_o + (rb2 >> 1) * 32 + korder(lane & 15) * 2 + (rb2 & 1);
        uint32_t ready = MODE == 0 ? 0u : ~0u;
#pragma unroll
        for (int i = MODE == 0 ? 2 : 0; i < 16; i++) {
          const int kb = korder(i), s = i % NS2, ph = (i / NS2) & 1;
          const uint32_t fb = bars + 8 * (BAR_FULL2 + s);
          if (!((ready >> i) & 1)) {
            int n = 0;
            do {
              ready |= __ballot_sync(0xffffffffu, ld_acquire(flag) == epoch);
            } while (!((ready >> i) & 1) && ++n < SPIN_LIMIT);
            fence_async_all();
          }
          if (i == 2) PROF(21);
          mbar_wait(bars + 8 * (BAR_EMPTY2 + s), ph);
          if (elect_one()) {
            mbar_expect_tx(fb, STG2);
            asm volatile(
                "cp.async.bulk.shared::cluster.global.mbarrier::complete_tx::bytes.multicast::cluster [%0], [%1], %2, [%3], %4;\n"
                ::"r"(sb + g2_a(s) + rank * 8192), "l"(osrc + kb * 16384), "r"(8192), "r"(fb), "h"((uint16_t)3) : "memory");
            if (MODE != 0 || i >= 4) tma_load_3d(sb + g2_b(s), &tmWo, fb, 0, kb * 64, cb2 * 2);
          }
          if (i == 3) PROF(37);

        }
      }
      __syncwarp();
    } else if (MODE != 2) {
      {
        const int g = lane >> 2, t = lane & 3;
        uint32_t w[2][4];
#pragma unroll
        for (int h = 0; h < 2; h++) {
          const uint2 x = __ldg(reinterpret_cast<const uint2*>(p.shift_k + ((chb & ~1) * 8 + h * 8 + g) * 4));
          w[h][0] = __byte_perm(x.x, x.x, 0x1010);
          w[h][1] = __byte_perm(x.x, x.x, 0x3232);
          w[h][2] = __byte_perm(x.y, x.y, 0x1010);
          w[h][3] = __byte_perm(x.y, x.y, 0x3232);
        }
        auto swz = [](int r) { return (((r & 29) | ((r ^ (r >> 2)) & 2)) << 5) | (r & 16); };
        const uint32_t kring = sb + OFF_H + (hw - 1) * 8192, vring = kring + 4096;
        const int s0 = rank * 32 + (hw - 1) * 11, s1 = hw == 3 ? rank * 32 + 32 : s0 + 11;
        const size_t goff = (size_t)(lane >> 1) * DM + (chb & ~1) * 8 + (lane & 1) * 8;
        const __nv_bfloat16* kg = p.k + goff;
        const __nv_bfloat16* vg = p.v + goff;
        const uint32_t d0 = swz(lane >> 1) ^ ((lane & 1) << 4), d1 = swz(16 + (lane >> 1)) ^ ((lane & 1) << 4);
        auto issue = [&](int st) {
          const uint32_t so = (st & 3) << 10;
          cp_async16(kring + so + d0, kg + (size_t)st * 32 * DM, 16);
          cp_async16(kring + so + d1, kg + (size_t)(st * 32 + 16) * DM, 16);
          cp_async16(vring + so + d0, vg + (size_t)st * 32 * DM, 16);
          cp_async16(vring + so + d1, vg + (size_t)(st * 32 + 16) * DM, 16);
        };
        const int xa = 8 * (lr >> 1) + 2 * lm + (lr & 1), xb = 8 * (lr >> 1) - 4 + 2 * (lm & 1) + (lr & 1);
        const uint32_t la = swz(xa), lb = swz(xb & 31);
        const int backb = xb < 0 ? 1 : 0;
        const uint32_t ud[2] = {mapa(sb + OFF_U + g * 4096 + t * 16, 0), mapa(sb + OFF_U + g * 4096 + t * 16, 1)};
        const uint32_t ub[2] = {mapa(bars + 8 * BAR_U, 0), mapa(bars + 8 * BAR_U, 1)};
        if (lane == 0) mbar_wait(bars + 8 * (BAR_FULLB + NS1B - 1), 0);
        __syncwarp();
        if (lane >= 24) cp_async16(kring + (((s0 - 1) & 3) << 10) + d1, s0 > 0 ? kg + (size_t)(s0 * 32 - 16) * DM : kg, s0 > 0 ? 16 : 0);
        issue(s0);
        asm volatile("cp.async.commit_group;\n" ::: "memory");
        issue(s0 + 1);
        asm volatile("cp.async.commit_group;\n" ::: "memory");
#pragma unroll 1
        for (int st = s0; st < s1; st++) {
          if (st + 2 < s1) issue(st + 2);
          if (hw == 1 && st - s0 < 8) prefetch_l2(p.ssm_k + (size_t)(chb * 8 + st - s0) * SEQ + lane * 64);
          if (hw == 2 && st == s0 + 4 && lane < 2) prefetch_l2(g_tab + (chb * 2 + lane) * 32);
          const uint32_t uo = (st ^ ((g ^ (st >> 2)) & 1)) * 64;
          asm volatile("cp.async.commit_group;\n" ::: "memory");
          asm volatile("cp.async.wait_group 2;\n" ::: "memory");
          __syncwarp();
#pragma unroll
          for (int h = 0; h < 2; h++) {
            uint32_t e[6], vv[4], e4[4];
            ldsm4t(e4, kring + ((st & 3) << 10) + (la ^ (h << 4)));
            ldsm2t(e[0], e[1], kring + (((st - backb) & 3) << 10) + (lb ^ (h << 4)));
            ldsm4t(vv, vring + ((st & 3) << 10) + (la ^ (h << 4)));
            e[2] = e4[0]; e[3] = e4[1]; e[4] = e4[2]; e[5] = e4[3];
            uint32_t o[5];
#pragma unroll
            for (int i = 0; i < 5; i++) o[i] = __byte_perm(e[i], e[i + 1], 0x5432);
#pragma unroll
            for (int i = 0; i < 4; i++) {
              uint32_t a = bmul2(o[i], w[h][3]);
              a = bfma2(e[i + 1], w[h][2], a);
              a = bfma2(o[i + 1], w[h][1], a);
              a = bfma2(e[i + 2], w[h][0], a);
              vv[i] = bmul2(a, vv[i]);
            }
            st_async128(ud[h] + uo, ub[h], vv[0], vv[1], vv[2], vv[3]);
          }
          __syncwarp();
        }
        PROF(16);
      }
      {
        const int rw = (lane >> 3) + (lane & 4), ck = lane & 3;
        const uint32_t so = rw * 64 + ck * 16, dof = rw * 128 + ((ck ^ rw) << 4);
        const uint8_t* hsrc = reinterpret_cast<const uint8_t*>(p.ssm_k + (size_t)chb * 8 * SEQ) + so;
        const float dv = lane < 8 ? __bfloat162float(p.ssm_D[chb * 8 + lane]) : 0.f;
        uint32_t x[32];
        auto load = [&](const uint8_t* src, int i) {
          asm volatile("ld.v4.u32 {%0,%1,%2,%3}, [%4];\n" : "=r"(x[4 * i]), "=r"(x[4 * i + 1]), "=r"(x[4 * i + 2]), "=r"(x[4 * i + 3])
                       : "l"(src + i * 512) : "memory");
        };
#pragma unroll
        for (int i = 0; i < 8; i++) load(hsrc + (hw - 1) * 4096, i);
        nb_sync(NB_HELP3, 96);
        mbar_wait(bars + 8 * BAR_U, 0);
        int eh = 0;
#pragma unroll 1
        for (int n = 2 * (hw - 1); n < 16; n += (n & 1) ? 5 : 1) {
          const int c = n >> 1;
          const uint8_t* nsrc = (n & 1) ? hsrc + (c < 5 ? c + 3 : c) * 4096
                                        : smem + OFF_U + c * 4096 + (so ^ (((c ^ (lane >> 2)) & 1) << 6));
          const uint32_t dst = sb + ((n & 1) ? OFF_U : OFF_H) + c * 4096 + dof;
          const float dc = __shfl_sync(0xffffffffu, dv, c);
          const float h0 = bf_lo(x[0]) + ((lane | (n & 1)) == 0 ? dc : 0.f), h1 = bf_hi(x[0]);
          x[0] = pack_bf16(h0, h1);
          uint32_t m[2] = {x[0], x[1]};
#pragma unroll
          for (int i = 2; i < 32; i++) asm("max.xorsign.abs.bf16x2 %0, %0, %1;\n" : "+r"(m[i & 1]) : "r"(x[i]));
          asm("max.xorsign.abs.bf16x2 %0, %0, %1;\n" : "+r"(m[0]) : "r"(m[1]));
          const uint32_t e = max(__reduce_max_sync(0xffffffffu, max((m[0] >> 7) & 255u, (m[0] >> 23) & 255u)), 5u);
          const uint32_t sc = (259u - e) * 0x00800080u;
#pragma unroll
          for (int i = 0; i < 8; i++) {
            uint32_t o[4];
#pragma unroll
            for (int j = 0; j < 4; j++) {
              const uint32_t v = bmul2(x[4 * i + j], sc);
              asm("cvt.rn.f16x2.f32 %0, %1, %2;\n" : "=r"(o[j]) : "f"(bf_hi(v)), "f"(i + j == 0 ? h0 * bf_hi(sc) : bf_lo(v)));
            }
            sts128((dst + (i & 3) * 1024) ^ ((i >> 2) << 6), o[0], o[1], o[2], o[3]);
            load(nsrc, i);
          }
          if (n & 1) {
            const int f = min(max((int)e + eh - 129, 0), 254);
            if (lane == 0) asm volatile("st.shared.u32 [%0], %1;\n" ::"r"(sb + OFF_SC + c * 4), "r"(f << 23) : "memory");
          }
          eh = e;
        }
        fence_async_smem();
        __syncwarp();
        if (lane == 0) mbar_arrive(bars + 8 * BAR_UH);
        PROF(32);
      }
      if (hw < 3) {
        const uint32_t rb = mapa(bars, lane & 1);
        const uint32_t epoch = ld_relaxed(g_flag_o + 2 * cta + hw - 1) + 1;
        const bool own = hw - 1 == (rb2 & 1);
        nb_sync(NB_OREADY + hw - 1, 160);
        if (lane == 0) {
          asm volatile("cp.async.bulk.global.shared::cta.bulk_group [%0], [%1], %2;\n" ::"l"(g_o + (size_t)cta * 16384 + (hw - 1) * 8192),
                       "r"(sb + OFF_OP + (own ? 16384 : 0)), "r"(16384) : "memory");
          bulk_commit();
        }
        if (lane < 2) {
          mbar_arrive_cluster(rb + 8 * (BAR_EMPTY2 + 2));
          mbar_arrive_cluster(rb + 8 * (BAR_EMPTY2 + 3));
        }
        if (lane == 0) {
          bulk_wait0();
          if (own) mbar_expect_tx(bars + 8 * (BAR_FULL2 + 1), 16384);
          mbar_arrive_cluster(mapa(bars, own ? rank : rank ^ 1) + 8 * BAR_X);
          st_release(g_flag_o + 2 * cta + hw - 1, epoch);
          mbar_arrive(bars + 8 * BAR_REL);
        }
        __syncwarp();
        PROF(17);
      } else {
        mbar_wait_idle(bars + 8 * BAR_REL, 0);
        if (MODE == 0) {
          mbar_wait(bars + 8 * BAR_X, 0);
          if (elect_one())
            asm volatile("cp.async.bulk.shared::cluster.shared::cta.mbarrier::complete_tx::bytes [%0], [%1], %2, [%3];\n"
                         ::"r"(mapa(sb + OFF_OP, rank ^ 1)), "r"(sb + OFF_OP + 16384), "r"(16384),
                         "r"(mapa(bars + 8 * BAR_FULL2, rank ^ 1)) : "memory");
        }
        if (MODE == 0) {
          mbar_wait_idle(bars + 8 * BAR_DEAD, 0);
          if (elect_one()) {
            tma_load_3d(sb + g2_b(2), &tmWo, bars + 8 * (BAR_FULL2 + 2), 0, g2_k(hp, 2) * 64, cb2 * 2);
            tma_load_3d(sb + g2_b(3), &tmWo, bars + 8 * (BAR_FULL2 + 3), 0, g2_k(hp, 3) * 64, cb2 * 2);
          }
        }
        __syncwarp();
      }
      {
        const int c8 = (4 * (lr >> 1) + 2 * (lm & 1) + (lr & 1)) & 7;
        const bool own = (lr >> 2) == rank;
        const uint32_t ya = sb + (own ? y_slot(c8 & 1, c8 >> 1) : OFF_LAND + c8 * 2048);
        const uint32_t yx = ((lm >> 1) ^ lr) << 4;
        const int row = (lane >> 3) * 8 + ((lane >> 2) & 1);
        uint2* og = reinterpret_cast<uint2*>(p.out + (size_t)(rank * 1024 + row) * (2 * DM) + (chb & ~1) * 8 + (lane & 3) * 4);
        const uint32_t qa = sb + OFF_Q + lane * 8;
        mbar_wait(bars + 8 * BAR_Q, 0);
        mbar_wait_idle(bars + 8 * BAR_LAND, 0);
        PROF(33);
        const uint32_t t0 = clock();
#pragma unroll 1
        for (int j = hw - 1; j < 16; j += 3) {
          uint32_t y[4][4];
          uint2 q[8];
          while ((uint32_t)clock() - t0 < j * PACE) __nanosleep(40);
          const uint32_t qj = qa + j * 2048;
#pragma unroll
          for (int i = 0; i < 4; i++) ldsm4t(y[i], ya + j * 128 + (yx ^ (i << 5)));
#pragma unroll
          for (int i = 0; i < 8; i++) q[i] = lds64(qj + i * 256);
#pragma unroll
          for (int i = 0; i < 8; i++)
            og[(size_t)(j * 64 + (i >> 2) * 32 + (i & 3) * 2) * (2 * DM / 4)] =
                make_uint2(bmul2(q[i].x, y[i >> 1][2 * (i & 1)]), bmul2(q[i].y, y[i >> 1][2 * (i & 1) + 1]));
        }
      }
      PROF(22);
    }
    cluster_sync_all();
  } else {
    asm volatile("setmaxnreg.inc.sync.aligned.u32 %0;\n" :: "n"(REG_MATH));
    if (warp == 0) PROF2(26);
    const int wg = warp >> 2;
    const int wtid = tid & 127;
    const bool signaller = (wtid == 0) || (wtid == 32);
    const uint32_t rbars = mapa(bars, wtid >> 5 & 1);

    if (halo_cta) {
      const uint32_t epoch = ld_relaxed(g_flag_h + blockIdx.x) + 1;
      float acc0[64], acc1[64];
      int s = 0, ph = 0;
#pragma unroll 1
      for (int kb = 0; kb < 16; kb++) {
        mbar_wait(bars + 8 * (BAR_FULLB + s), ph);
        const uint32_t st = sb + s * STGH;
        const uint64_t da = mkdesc(st, 16, 1024, 1);
        const uint64_t db = mkdesc(st + 8192 + wg * 32768, 8192, 1024, 1);
        wg_fence();
#pragma unroll
        for (int kk = 0; kk < 4; kk++) {
          wgmma_n128(acc0, da + 2 * kk, db + 128 * kk, kb + kk);
          wgmma_n128(acc1, da + 2 * kk, db + 1024 + 128 * kk, kb + kk);
        }
        wg_commit();
        wg_wait<0>();
        if (wtid == 0) mbar_arrive(bars + 8 * (BAR_EMPTYB + s));
        if (++s == 3) { s = 0; ph ^= 1; }
      }
      fence_regs(acc0);
      fence_regs(acc1);
      if ((warp & 3) != 3) {
#pragma unroll
        for (int hh = 0; hh < 2; hh++) {
          uint4* dst = g_halo + ((hh * 4 + (warp & 3) + 1) * 16 + blockIdx.x * 4) * 128 + wg * 64 + lane;
#pragma unroll
          for (int j = 0; j < 4; j++) {
            const int o = 16 * j + 2 * hh;
            dst[(j >> 1) * 128 + (j & 1) * 32] =
                make_uint4(pack_bf16(acc0[o], acc0[o + 1]), pack_bf16(acc0[o + 4], acc0[o + 5]),
                           pack_bf16(acc0[o + 8], acc0[o + 9]), pack_bf16(acc0[o + 12], acc0[o + 13]));
            dst[(2 + (j >> 1)) * 128 + (j & 1) * 32] =
                make_uint4(pack_bf16(acc1[o], acc1[o + 1]), pack_bf16(acc1[o + 4], acc1[o + 5]),
                           pack_bf16(acc1[o + 8], acc1[o + 9]), pack_bf16(acc1[o + 12], acc1[o + 13]));
          }
        }
      }
      nb_sync(NB_G1DONE, 256);
      if (tid == 0) st_release(g_flag_h + blockIdx.x, epoch);
      PROF(36);
      cluster_sync_all();
      return;
    }

    float acc[64];
    auto g2_step = [&](int s, int kb) {
      const uint64_t da = mkdesc(sb + g2_a(s) + wg * 8192, 16, 1024, 1);
      const uint64_t db = mkdesc(sb + g2_b(s), 8192, 1024, 1);
      wg_fence();
      wgmma_n128(acc, da, db, kb);
      wgmma_n128(acc, da + 2, db + 128, 1);
      wgmma_n128(acc, da + 4, db + 256, 1);
      wgmma_n128(acc, da + 6, db + 384, 1);
      wg_commit();
    };

    if (MODE != 2) {
    uint32_t a1[2][4], tw[16], d1[32];
    const uint32_t tb = sb + OFF_T + wtid * 16;
    const uint64_t dx = mkdesc(sb + OFF_U + wg * 4096, OFF_H - OFF_U, 1024, 1);
    auto s1 = [&](int it) {
      hmma_n128t<0>(d1, a1[0], dx + it * 512);
      hmma_n128t<1>(d1, a1[1], dx + it * 512 + 128);
      wg_commit();
    };
    auto ldtw = [&](int i) {
      const uint4 v = lds128(tb + T_TW + i * 2048);
      tw[4 * i] = v.x; tw[4 * i + 1] = v.y; tw[4 * i + 2] = v.z; tw[4 * i + 3] = v.w;
    };
    {
      float acc0[96], acc1[96];
      int sa = 0, pha = 0, sbb = 0, phb = 0;
      asm volatile("cp.async.wait_group 0;\n" ::: "memory");
      fence_async_smem();
      nb_sync(NB_FIRST, 256);
      if (tid == 0) {
        mbar_arrive(bars + 8 * BAR_FULLA);
        mbar_arrive(bars + 8 * BAR_FULLB);
      }
      PROF(0 + wg);
#pragma unroll 1
      for (int kb = 0; kb < 30; kb++) {
        if (!(kb & 1)) mbar_wait(bars + 8 * (BAR_FULLA + sa), pha);
        mbar_wait(bars + 8 * (BAR_FULLB + sbb), phb);
        if (kb == 0) PROF2(0 + wg);
        if (kb == 4 && wg == 0) PROF2(28);
        if (kb == 8 && wg == 0) PROF2(29);
        if (kb == 16 && wg == 0) PROF2(30);
        const uint64_t da = mkdesc(sb + sa * STG1A + wg * 16384 + (kb & 1) * 64, 16, 1024, 1);
        const uint64_t db = mkdesc(sb + OFF_1B + sbb * STG1B, 4096, 1024, 1);
        wg_fence();
        wgmma_n192(acc0, da, db, kb);
        wgmma_n192(acc1, da + 512, db, kb);
        wgmma_n192(acc0, da + 2, db + 128, 1);
        wgmma_n192(acc1, da + 514, db + 128, 1);
        wg_commit();
        wg_wait<1>();
        if (kb > 0) {
          if (wtid == 64) mbar_arrive(bars + 8 * (BAR_EMPTYB + (sbb == 0 ? NS1B - 1 : sbb - 1)));
          if (!(kb & 1) && signaller) mbar_arrive_cluster(rbars + 8 * (BAR_EMPTYA + (sa == 0 ? NS1A - 1 : sa - 1)));
        }
        if (++sbb == NS1B) { sbb = 0; phb ^= 1; }
        if ((kb & 1) && ++sa == NS1A) { sa = 0; pha ^= 1; }
      }
      const int blk0 = wg * 8 + (warp & 3);
      const int lr = lane & 7, lm = lane >> 3;
      const bool le0 = 2 * (lane & 3) <= (lane >> 2), le1 = 2 * (lane & 3) + 1 <= (lane >> 2);
      const uint32_t maskLE = (le0 ? 0x0000FFFFu : 0u) | (le1 ? 0xFFFF0000u : 0u);
      uint32_t k0[2][2][4], k1[2][2][4], qa[2][2][8];
      float l[2][2][4];
      {
        static_assert(15 % NS1A == 0 && 30 % NS1B == 0, "slots of the last k blocks");
        mbar_wait(bars + 8 * BAR_FULLA, 1);
        mbar_wait(bars + 8 * BAR_FULLB, 0);
        mbar_wait(bars + 8 * (BAR_FULLB + 1), 0);
        const uint64_t da = mkdesc(sb + wg * 16384, 16, 1024, 1);
        const uint64_t db = mkdesc(sb + OFF_1B, 4096, 1024, 1);
        wg_fence();
#pragma unroll
        for (int i = 0; i < 4; i++) wgmma_n192(acc0, da + 2 * i, db + (i >> 1) * (STG1B >> 4) + (i & 1) * 128, 1);
        wg_commit();
        wg_wait<1>();
        if (wtid == 64) mbar_arrive(bars + 8 * (BAR_EMPTYB + NS1B - 1));
#pragma unroll
        for (int i = 0; i < 2; i++) wgmma_n192(acc1, da + 512 + 2 * i, db + (i >> 1) * (STG1B >> 4) + (i & 1) * 128, 1);
        wg_commit();
        wg_wait<1>();
        fence_regs(acc0);
        attn_stage(sb, blk0, lane, acc0, k1[0]);
#pragma unroll
        for (int i = 2; i < 4; i++) wgmma_n192(acc1, da + 512 + 2 * i, db + (i >> 1) * (STG1B >> 4) + (i & 1) * 128, 1);
        wg_commit();
        attn_pack(acc0, qa[0], k0[0]);
        wg_wait<0>();
        fence_regs(acc1);
      }
      if (wtid == 64) mbar_arrive(bars + 8 * BAR_EMPTYB);
      PROF(2 + wg);
      attn_stage(sb, blk0 + 4, lane, acc1, k1[1]);
      __syncwarp();
      if (lane == 0) mbar_arrive(bars + 8 * BAR_STG);
      mbar_wait(bars + 8 * BAR_U, 0);
      attn_pack(acc1, qa[1], k0[1]);
      attn_own(k0[0], k1[0], le0, le1, qa[0], l[0]);
      attn_own(k0[1], k1[1], le0, le1, qa[1], l[1]);
      const uint32_t cho[2] = {(uint32_t)(((lm & 1) ^ lr) << 4), (uint32_t)(((2 + (lm & 1)) ^ lr) << 4)};
      const uint32_t obase = sb + OFF_OP + (wg == (rb2 & 1) ? 16384 : 0) + ((warp & 3) * 16 + lr) * 128;
      mbar_wait(bars + 8 * BAR_STG, 0);
      {
        uint32_t km[4][4], va[8][4], vb[8][4], pp[8];
        float x[8][2];
#pragma unroll
        for (int n = 0; n < 4; n++) {
          const int blk = blk0 + 4 * (n >> 1);
          to_arr(km[n], lds128(sb + (blk == 0 ? OFF_L0 + 1024 : OFF_KH + (blk - 1) * 2048) + (n & 1) * 512 + lane * 16));
        }
#pragma unroll
        for (int n = 0; n < 8; n++) {
          const int vr = (blk0 + 4 * ((n >> 1) & 1)) * 16 - 8 + 8 * (n >> 2) + 8 * (lm >> 1);
          const uint32_t vrow = sb + (vr < 0 ? OFF_L0 : OFF_VP + vr * 128) + lr * 128;
          ldsm4t(va[n], vrow + (cho[0] ^ ((n & 1) << 6)));
          ldsm4t(vb[n], vrow + (cho[1] ^ ((n & 1) << 6)));
        }
        const bool first = blk0 == 0 && gidx == 0;
#pragma unroll
        for (int n = 0; n < 4; n++) {
          const uint32_t(&q)[8] = qa[n >> 1][n & 1];
          float sm[4];
          mma16816_z(sm, q[0], q[1], q[2], q[3], km[n][0], km[n][1]);
          mma16816(sm, q[4], q[5], q[6], q[7], km[n][2], km[n][3]);
          if (n < 2 && first) sm[0] = sm[1] = -1e9f / 0.17677669529663687f;
          x[n][0] = le0 ? l[n >> 1][n & 1][0] : sm[0];
          x[n][1] = le1 ? l[n >> 1][n & 1][1] : sm[1];
          x[4 + n][0] = l[n >> 1][n & 1][2];
          x[4 + n][1] = l[n >> 1][n & 1][3];
        }
        quad_softmax<8>(x, pp);
#pragma unroll
        for (int n = 7; n >= 0; n--)
          attn_pv(obase + ((n >> 1) & 1) * 8192 + (n >> 2) * 1024 + (((4 * (n & 1) + lm) ^ lr) << 4), va[n], vb[n], pp[n],
                  maskLE);
      }
      fence_async_smem();
      nb_arrive(NB_OREADY + wg, 160);
    }

    {
      const int w = warp & 3;
      uint32_t a4[8][4];
      float d4[16];
      PROF(34 + wg);
      const uint64_t dz = mkdesc(sb + OFF_U + wg * 4096, 512, 128, 0);
      const uint64_t db2 = mkdesc(sb + OFF_T + T_B2, 128, 256, 0);
      mbar_wait(bars + 8 * BAR_T, 0);
      mbar_wait(bars + 8 * BAR_UH, 0);
      to_arr(a1[0], lds128(tb + T_A1));
      to_arr(a1[1], lds128(tb + T_A1 + 2048));
      wg_fence();
      s1(0);
      ldtw(0);
      ldtw(1);
      const uint32_t za = sb + (w < 2 ? OFF_U : OFF_H) + wg * 4096 + (w & 1) * 2048 + lane * 16;
      const uint32_t yl = (wtid ^ (4 * rank + wg)) * 16;
      const uint32_t yown = mapa(sb, rank) + yl, yrem = mapa(sb + OFF_LAND + wg * 2048, rank ^ 1) + yl;
      const uint32_t yb[2] = {mapa(bars + 8 * BAR_LAND, 0), mapa(bars + 8 * BAR_LAND, 1)};
      wg_wait<0>();
      fence_regs(d1);
      nb_sync(NB_WG + wg, 128);
      auto s4 = [&](int it) {
        wg_fence();
#pragma unroll
        for (int ks = 0; ks < 8; ks++) {
          const uint64_t d = dz + (it & 1) * 512 + (ks & 3) * 64 + (ks >> 2) * ((OFF_H - OFF_U) >> 4);
          if (ks == 0) fmma_n32t<0>(d4, a4[ks], d);
          else fmma_n32t<1>(d4, a4[ks], d);
        }
        wg_commit();
      };
      auto e4 = [&](int it) {
        fence_regs(d4);
        const float sc = __uint_as_float(lds32(sb + OFF_SC + wg * 4 + it * 8));
        uint32_t r[8];
#pragma unroll
        for (int i = 0; i < 8; i++) r[i] = pack_bf16(d4[2 * i] * sc, d4[2 * i + 1] * sc);
        const uint32_t o = (yown + y_slot(wg, it)) ^ ((it >> 1) << 5), m = (yrem + it * 4096) ^ ((it >> 1) << 5);
        if (it == 0) mbar_wait(bars + 8 * BAR_LFREE, 0);
        if (it == 3) mbar_wait(bars + 8 * (BAR_DEAD + 1), 0);
        st_async128(rank ? m : o, yb[0], r[0], r[2], r[1], r[3]);
        st_async128(rank ? o : m, yb[1], r[4], r[6], r[5], r[7]);
      };
      uint32_t a2[2][2][2][4], a3[2][2][4], d2[2][2][8], d3[2][8];
      auto s2a = [&]() {
        wg_fence();
#pragma unroll
        for (int c = 0; c < 4; c++) hmma_n32<0, 0>(d2[c & 1][c >> 1], a2[0][c & 1][c >> 1], db2 + (c >> 1) * 128);
      };
      auto s2b = [&]() {
        wg_fence();
#pragma unroll
        for (int c = 0; c < 4; c++) {
          hmma_n32<1, 0>(d2[c & 1][c >> 1], a2[1][c & 1][c >> 1], db2 + (c >> 1) * 128 + 64);
          if (c & 1) wg_commit();
        }
      };
      auto done = [&](int it) {
        if (it == 0) {
          if (signaller) mbar_arrive_cluster(rbars + 8 * BAR_LFREE);
        } else if (it >= 2 && wtid == 64) {
          mbar_arrive(bars + 8 * (BAR_DEAD + it - 2));
        }
        if (w == 0) PROF3(40 + 4 * wg + it);
      };
      fft_e1<0>(d1, tw, a2[0]);
      s2a();
      fft_e1<1>(d1, tw, a2[1]);
      s2b();
      s1(1);
      ldtw(2);
      ldtw(3);
#pragma unroll
      for (int i = 0; i < 8; i++) to_arr(a4[i], lds128(tb + T_A4 + i * 2048));
#pragma unroll
      for (int it = 0; it < 4; it++) {
        if (it == 0 || it == 3) wg_wait<2>(); else wg_wait<3>();
        fence_regs(d2[0][0]);
        fence_regs(d2[1][0]);
        fft_e2<0, 0>(d2[0][0], d2[1][0], a3[0]);
        fft_e2<0, 1>(d2[0][0], d2[1][0], a3[1]);
        if (it == 0 || it == 3) wg_wait<1>(); else wg_wait<2>();
        fence_regs(d2[0][1]);
        fence_regs(d2[1][1]);
        fft_e2<1, 0>(d2[0][1], d2[1][1], a3[0]);
        fft_e2<1, 1>(d2[0][1], d2[1][1], a3[1]);
        wg_fence();
        hmma_n32<0, 0>(d3[0], a3[0][0], db2);
        hmma_n32<0, 0>(d3[1], a3[0][1], db2);
        hmma_n32<1, 0>(d3[0], a3[1][0], db2 + 64);
        hmma_n32<1, 0>(d3[1], a3[1][1], db2 + 64);
        wg_commit();
        wg_wait<1>();
        if (it > 0) e4(it - 1);
        if (it < 3) {
          fence_regs(d1);
          fft_e1<0>(d1, tw, a2[0]);
        }
        wg_wait<0>();
        fence_regs(d3[0]);
        fence_regs(d3[1]);
        if (it < 3) s2a();
        fft_e3(d3, tw, za + (it & 1) * 8192);
        if (it < 3) {
          fft_e1<1>(d1, tw, a2[1]);
          s2b();
        }
        fence_async_smem();
        nb_sync(NB_WG + wg, 128);
        done(it);
        s4(it);
        if (it < 2) s1(it + 2);
      }
      if (PEEL && MODE == 0) {
        mbar_wait(bars + 8 * BAR_FULL2, 0);
        g2_step(0, 0);
        wg_wait<1>();
      } else {
        wg_wait<0>();
      }
      if (signaller) mbar_arrive_cluster(rbars + 8 * (BAR_EMPTY2 + 4));
      e4(3);
      if (PEEL && MODE == 0) {
        wg_wait<0>();
        if (signaller) mbar_arrive_cluster(rbars + 8 * BAR_EMPTY2);
      }
      PROF(6 + wg);
    }
    }

    if (MODE != 1) {
      int s = PEEL && MODE == 0, ph = 0;
#pragma unroll 1
      for (int kb = s; kb < 16; kb++) {
        mbar_wait(bars + 8 * (BAR_FULL2 + s), ph);
        if (kb == 1) PROF(8 + wg);
        if (warp == 4) PROF2(40 + kb);
        g2_step(s, kb);
        wg_wait<0>();
        if (kb < 16 - NS2 && signaller) mbar_arrive_cluster(rbars + 8 * (BAR_EMPTY2 + s));
        if (++s == NS2) { s = 0; ph ^= 1; }
      }
      wg_wait<0>();
      fence_regs(acc);
      PROF(10 + wg);
      const int lr = lane & 7, lm = lane >> 3;
      const uint32_t wbase = sb + warp * 2048;
      const uint32_t base = wbase + (lr + 8 * (lm & 1)) * 128;
#pragma unroll
      for (int j = 0; j < 16; j += 2) {
        const uint32_t a = base + (j >> 3) * 16384 + ((((j & 7) + (lm >> 1)) ^ lr) << 4);
        stsm4(a, pack_bf16(acc[4 * j], acc[4 * j + 1]), pack_bf16(acc[4 * j + 2], acc[4 * j + 3]),
              pack_bf16(acc[4 * j + 4], acc[4 * j + 5]), pack_bf16(acc[4 * j + 6], acc[4 * j + 7]));
      }
      __syncwarp();
      {
        const int rr = lane >> 4, ck = lane & 7, hf = (lane >> 3) & 1;
        uint4* og = reinterpret_cast<uint4*>(p.out + (size_t)(2 * ((rb2 & 7) * 128 + warp * 16 + rr) + (rb2 >> 3)) * (2 * DM) + DM + cb2 * 128 + hf * 64 + ck * 8);
        uint4 v[8];
#pragma unroll
        for (int i = 0; i < 8; i++) v[i] = lds128(wbase + hf * 16384 + (2 * i + rr) * 128 + ((ck ^ ((2 * i + rr) & 7)) << 4));
#pragma unroll
        for (int i = 0; i < 8; i++) og[(size_t)i * 4 * (2 * DM / 8)] = v[i];
      }
      PROF(12 + wg);
    }
    cluster_sync_all();
  }
}

typedef CUresult (*EncodeFn)(CUtensorMap*, CUtensorMapDataType, cuuint32_t, void*, const cuuint64_t*, const cuuint64_t*,
                             const cuuint32_t*, const cuuint32_t*, CUtensorMapInterleave, CUtensorMapSwizzle,
                             CUtensorMapL2promotion, CUtensorMapFloatOOBfill);

void make_map(EncodeFn enc, CUtensorMap* tm, const void* base, int rank, const cuuint64_t* dims, const cuuint64_t* strides,
              const cuuint32_t* box, CUtensorMapSwizzle swz) {
  cuuint32_t es[5] = {1, 1, 1, 1, 1};
  enc(tm, CU_TENSOR_MAP_DATA_TYPE_BFLOAT16, rank, const_cast<void*>(base), dims, strides, box, es,
      CU_TENSOR_MAP_INTERLEAVE_NONE, swz, CU_TENSOR_MAP_L2_PROMOTION_L2_256B, CU_TENSOR_MAP_FLOAT_OOB_FILL_NONE);
}

}

extern "C" void kernel_launch(void* const* d_in, const int* in_sizes, int n_in, void* d_out, int out_size) {
  static EncodeFn enc = nullptr;
  static bool coresident = true;
  if (!enc) {
    void* fn = nullptr;
    cudaDriverEntryPointQueryResult qr;
    cudaGetDriverEntryPoint("cuTensorMapEncodeTiled", &fn, cudaEnableDefault, &qr);
    enc = (EncodeFn)fn;
    cudaFuncSetAttribute(fused_kernel<0>, cudaFuncAttributeMaxDynamicSharedMemorySize, SMEM_BYTES);
    cudaFuncSetAttribute(fused_kernel<1>, cudaFuncAttributeMaxDynamicSharedMemorySize, SMEM_BYTES);
    cudaFuncSetAttribute(fused_kernel<2>, cudaFuncAttributeMaxDynamicSharedMemorySize, SMEM_BYTES);
    cudaLaunchConfig_t cfg = {};
    cfg.gridDim = dim3(NCTA);
    cfg.blockDim = dim3(NTHREADS);
    cfg.dynamicSmemBytes = SMEM_BYTES;
    cudaLaunchAttribute at;
    at.id = cudaLaunchAttributeClusterDimension;
    at.val.clusterDim.x = 2;
    at.val.clusterDim.y = 1;
    at.val.clusterDim.z = 1;
    cfg.attrs = &at;
    cfg.numAttrs = 1;
    int nclusters = 0;
    if (cudaOccupancyMaxActiveClusters(&nclusters, fused_kernel<0>, &cfg) == cudaSuccess) coresident = nclusters >= NCTA / 2;
    (void)cudaGetLastError();
  }
  CUtensorMap tmX, tmW, tmWo, tmQ, tmXh, tmWh;
  {
    cuuint64_t dims[3] = {1024, 2, 1024};
    cuuint64_t str[2] = {2048, 4096};
    cuuint32_t box[3] = {64, 1, 128};
    make_map(enc, &tmX, d_in[6], 3, dims, str, box, CU_TENSOR_MAP_SWIZZLE_128B);
  }
  {
    cuuint64_t dims[3] = {1024, 1024, 3};
    cuuint64_t str[2] = {6144, 2048};
    cuuint32_t box[3] = {64, 32, 3};
    make_map(enc, &tmW, d_in[7], 3, dims, str, box, CU_TENSOR_MAP_SWIZZLE_128B);
  }
  {
    cuuint64_t dims[3] = {64, 1024, 16};
    cuuint64_t str[2] = {2048, 128};
    cuuint32_t box[3] = {64, 64, 2};
    make_map(enc, &tmWo, d_in[8], 3, dims, str, box, CU_TENSOR_MAP_SWIZZLE_128B);
  }
  {
    cuuint64_t dims[5] = {1024, 2, 4, 4, 64};
    cuuint64_t str[4] = {2048, 8 * 2048, 2 * 2048, 32 * 2048};
    cuuint32_t box[5] = {16, 2, 4, 4, 4};
    make_map(enc, &tmQ, d_in[0], 5, dims, str, box, CU_TENSOR_MAP_SWIZZLE_NONE);
  }
  {
    cuuint64_t dims[4] = {1024, 256, 2, 4};
    cuuint64_t str[3] = {4096, 2048, 256 * 4096};
    cuuint32_t box[4] = {64, 8, 2, 4};
    make_map(enc, &tmXh, d_in[6], 4, dims, str, box, CU_TENSOR_MAP_SWIZZLE_128B);
  }
  {
    cuuint64_t dims[3] = {64, 1024, 48};
    cuuint64_t str[2] = {6144, 128};
    cuuint32_t box[3] = {64, 64, 4};
    make_map(enc, &tmWh, d_in[7], 3, dims, str, box, CU_TENSOR_MAP_SWIZZLE_128B);
  }
  Params p;
  p.q = (const __nv_bfloat16*)d_in[0];
  p.k = (const __nv_bfloat16*)d_in[1];
  p.v = (const __nv_bfloat16*)d_in[2];
  p.shift_k = (const __nv_bfloat16*)d_in[3];
  p.ssm_k = (const __nv_bfloat16*)d_in[4];
  p.ssm_D = (const __nv_bfloat16*)d_in[5];
  p.x = (const __nv_bfloat16*)d_in[6];
  p.w = (const __nv_bfloat16*)d_in[7];
  p.wo = (const __nv_bfloat16*)d_in[8];
  p.out = (__nv_bfloat16*)d_out;
  if (coresident) {
    fused_kernel<0><<<NCTA, NTHREADS, SMEM_BYTES>>>(p, tmX, tmW, tmWo, tmQ, tmXh, tmWh);
  } else {
    fused_kernel<0><<<4, NTHREADS, SMEM_BYTES>>>(p, tmX, tmW, tmWo, tmQ, tmXh, tmWh);
    fused_kernel<1><<<NCTA, NTHREADS, SMEM_BYTES>>>(p, tmX, tmW, tmWo, tmQ, tmXh, tmWh);
    fused_kernel<2><<<NCTA, NTHREADS, SMEM_BYTES>>>(p, tmX, tmW, tmWo, tmQ, tmXh, tmWh);
  }
}
```

```cpp
#include <cuda_runtime.h>
#include <cuda.h>
#include <cuda_bf16.h>
#include <stdint.h>

namespace {

constexpr int SEQ = 2048;
constexpr int DM = 1024;
constexpr int NCTA = 132;
constexpr int NTHREADS = 384;

constexpr int STG1A = 32768;
constexpr int NS1A = 3;
constexpr int STG1B = 12288;
constexpr int NS1B = 5;
constexpr int OFF_1B = NS1A * STG1A;
constexpr int STG2 = 32768;
constexpr int NS2 = 5;
constexpr int STGH = 73728;
constexpr int OFF_VP = 0;
constexpr int OFF_KH = 1 * STG2;
constexpr int OFF_OP = 2 * STG2;
constexpr int OFF_Q = 3 * STG2;
constexpr int T_A4 = 0, T_TW = 16384, T_B2 = 24576, T_A1 = 28672, T_END = 32768;
constexpr int OFF_U = 163840;
constexpr int OFF_H = OFF_U + 32768;
constexpr int OFF_T = OFF_U - T_END;
constexpr int OFF_LAND = 4 * STG2;
constexpr int OFF_BAR = OFF_H + 32768;
constexpr int OFF_SC = OFF_BAR + 512;
constexpr int OFF_L0 = OFF_BAR + 1024;
constexpr int SMEM_BYTES = OFF_L0 + 2048;
static_assert(OFF_T + T_A1 == OFF_1B + NS1B * STG1B && OFF_T + T_TW == OFF_1B + 4 * STG1B && OFF_LAND == OFF_T + T_A4, "layout");
static_assert(3 * STGH <= OFF_BAR && SMEM_BYTES <= 232448, "smem");

constexpr int BAR_FULLA = 0;
constexpr int BAR_EMPTYA = 3;
constexpr int BAR_FULLB = 6;
constexpr int BAR_EMPTYB = 11;
constexpr int BAR_FULL2 = 16;
constexpr int BAR_EMPTY2 = 21;
constexpr int BAR_T = 26;
constexpr int BAR_UH = 27;
constexpr int BAR_LFREE = 28;
constexpr int BAR_LAND = 29;
constexpr int BAR_U = 30;
constexpr int BAR_Q = 31;
constexpr int BAR_STG = 32;
constexpr int BAR_DEAD = 33;
constexpr int BAR_X = 35;
constexpr int BAR_REL = 36;

constexpr int NB_G1DONE = 1;
constexpr int NB_OREADY = 2;
constexpr int NB_WG = 4;
constexpr int NB_HELP3 = 6;
constexpr int NB_FIRST = 7;
constexpr int NB_LEAD = 8;

#define PACE 390u
#define PF0 20
#define EARLYS1 0
#define PEEL 1
#define IDLEW 1
#define WAVE 0
#define LA0 3
#define LA1 4
#define STAG 12
#define LAST 0
#define FINE 40
#define SCHED 1
#define REG_MATH 224
#define REG_HELP 56
constexpr int SPIN_LIMIT = 1 << 20;

__device__ __align__(1024) __nv_bfloat16 g_o[SEQ * DM];
__device__ uint32_t g_flag_o[256];
__device__ uint32_t g_flag_h[4];
__device__ uint4 g_halo[128 * 128];
__device__ __align__(128) const uint32_t g_tab[T_END / 4] = {
0x3c003c00,0x3bf13bff,0,0xafd6a648,0x3c003c00,0x3b993bce,0,0xb505b303,0x3c003c00,0x3af63b50,0,0xb7e3b67c,
0x3c003c00,0x3a0f3a8a,0,0xb93ab89b,0x3bc33bfe,0x3b773bfa,0xb3c6aa48,0xb5c2acb5,0x3a6d3b3b,0x389b3a4f,0xb8c4b6d7,0xba8ab8ec,
0x381d395f,0x26483505,0xbaddb9ed,0xbbffbb99,0x30b23564,0xb848b444,0xbbeabb88,0xbac2bbb6,0x3b0e3bf6,0x3a8a3bf1,0xb78bae46,0xb89bafd6,
0x34a53913,0xa6483732,0xbba8ba2f,0xbbffbb25,0xb78bae46,0xbac2b7e3,0xbb0ebbf6,0xb848baf6,0xbba8ba2f,0xbb50bbfa,0xb4a5b913,0x367cacb5,
0x39ed3bea,0x393a3be2,0xb95fb0b2,0xba0fb179,0xb56433c6,0xb8ec2648,0xbb88bbc3,0xba4fbbff,0xbbfeba6d,0xbb25bbce,0xaa48b8c4,0x3732b303,
0xb6d7badd,0x3444b67c,0x3b3b381d,0x3bb63b50,0x38723bd9,0x37323bce,0xbaa7b23e,0xbb25b303,0xbaa7b23e,0xbbb6b67c,0xb872bbd9,0xb444bb50,
0xb872bbd9,0xacb5ba8a,0x3aa7323e,0x3bfa389b,0x3aa7323e,0x3bf139cb,0x38723bd9,0xafd63984,0x35643bc3,0x33033bb6,0xbb88b3c6,0xbbceb444,
0xbbfeb8c4,0xbb77ba0f,0x2a48ba6d,0x35c2b93a,0x36d7b81d,0x3a8aafd6,0x3b3b3add,0x389b3bf1,0x395f3bea,0x26483b25,0xb9ed30b2,0xbbffb732,
0x2e463ba8,0xa6483b99,0xbbf6b4a5,0xbbffb505,0xba2fbb0e,0xb848bbb6,0x3913b78b,0x3ac2b444,0x3bf634a5,0x3b50393a,0x2e463ba8,0xb67c3a0f,
0xb913378b,0xbbe2afd6,0xba2fbb0e,0xb179bbf1,0xb0b23b88,0xb4443b77,0xbbeab564,0xbbb6b5c2,0xb3c6bbfe,0x2cb5bbe2,0x3bc3aa48,0x3bfa3179,
0x38c43b3b,0x2fd63bff,0xba6d36d7,0xbbf12648,0xbaddb95f,0xb505bbce,0x381db9ed,0x3b99b303,0xb61f3b64,0xb7e33b50,0xbb64b61f,0xbaf6b67c,
0x361fbb64,0x393aba8a,0x3b64361f,0x3a0f389b,0xb61f3b64,0xba4f3984,0xbb64b61f,0xb8ecb9cb,0x361fbb64,0x3b25b848,0x3b64361f,0x37323ac2,
0xb8c43b3b,0xb9843b25,0xba6db6d7,0xb9cbb732,0x3addb95f,0x3bceb7e3,0x381d39ed,0x33033af6,0xbbea3564,0xbb77acb5,0xb0b2bb88,0x35c2bbfa,
0x3bc32a48,0x389b38ec,0xb3c63bfe,0xba8a3a4f,0xba2f3b0e,0xbac23af6,0xb913b78b,0xb848b7e3,0x3bf6b4a5,0x3b50acb5,0xae463ba8,0xb67c3bfa,
0xb913b78b,0xb179ba4f,0x3a2fbb0e,0x3be2b8ec,0xae463ba8,0xb9cb3b99,0xbbf634a5,0xb984b505,0xbb3b3add,0xbb993ac2,0xb6d7b81d,0xb505b848,
0x39ed30b2,0x37e335c2,0xb95f3bea,0xbaf63b77,0x3564bbc3,0x3a0fbbe2,0x3b88b3c6,0x393a3179,0xbbfe38c4,0xba4f2648,0xaa48ba6d,0x38ecbbff,
0xbbd93aa7,0xbbfa3a8a,0xb23eb872,0xacb5b89b,0x323e3872,0xafd639cb,0xbbd93aa7,0xbbf13984,0x3bd9baa7,0x3b99b848,0x323e3872,0xb5053ac2,
0xb23eb872,0x37e3bb77,0x3bd9baa7,0x3af6b5c2,0xbbfe3a6d,0xbbe23a4f,0x2a48b8c4,0x3179b8ec,0xb6d73add,0xb9843b99,0xbb3b381d,0xb9cb3505,
0x395fb0b2,0x33033444,0xb9ed3bea,0xbbce3bb6,0x3b88bbc3,0x3b77b93a,0x356433c6,0xb5c23a0f,0xbba83a2f,0xbb503a0f,0x34a5b913,0x367cb93a,
0xbb0e3bf6,0xbbe23bf1,0xb78b2e46,0xb179afd6,0xb4a53913,0xb9cb3b25,0xbba83a2f,0xb9843732,0x378bae46,0xb30337e3,0xbb0e3bf6,0xbbce3af6,
0xbadd39ed,0xba4f39cb,0x381db95f,0x38ecb984,0xbbea3b88,0xbb253ac2,0x30b2b564,0x3732b848,0xbbc33bfe,0xbbb63b77,0xb3c62a48,0x3444b5c2,
0xba6d3b3b,0xbbfa3be2,0xb8c436d7,0x2cb5b179,0xb9a839a8,0xb8ec3984,0x39a8b9a8,0x3a4fb9cb,0xb9a839a8,0xb7323848,0x39a8b9a8,0x3b25bac2,
0xb9a839a8,0xb44435c2,0x39a8b9a8,0x3bb6bb77,0xb9a839a8,0xacb53179,0x39a8b9a8,0x3bfabbe2,0xb81d395f,0xb67c393a,0x3addb9ed,0x3b50ba0f,
0xb0b23564,0x31792fd6,0x3beabb88,0x3be2bbf1,0x33c6aa48,0x3984b732,0x3bc3bbfe,0x39cbbb25,0x38c4b6d7,0x3bcebaf6,0x3a6dbb3b,0x3303b7e3,
0xb4a53913,0xb17938ec,0x3ba8ba2f,0x3be2ba4f,0x378bae46,0x39cbb505,0x3b0ebbf6,0x3984bb99,0x3ba8ba2f,0x3bcebbb6,0x34a5b913,0xb303b444,
0x3b0ebbf6,0x35c2ba0f,0xb78b2e46,0xbb77393a,0xaa4838c4,0x2cb5389b,0x3bfeba6d,0x3bfaba8a,0x3b3bb81d,0x3bf1b984,0x36d7badd,0x2fd6b9cb,
0x39edbbea,0x3505bac2,0xb95f30b2,0xbb993848,0xb564b3c6,0xbaf635c2,0xbb883bc3,0xb7e33b77,0x323e3872,0x35053848,0x3bd9baa7,0x3b99bac2,
0x3bd9baa7,0x3af6bb77,0xb23eb872,0xb7e3b5c2,0xb23eb872,0xb93ab179,0xbbd93aa7,0xba0f3be2,0xbbd93aa7,0xb8ec3bff,0x323e3872,0x3a4fa648,
0x36d7381d,0x384837e3,0x3b3bbadd,0x3ac2baf6,0x395fbbea,0x367cbbfa,0xb9edb0b2,0xbb502cb5,0xbb8833c6,0xbbe238ec,0xb5643bc3,0x31793a4f,
0x2a483a6d,0x39843505,0x3bfeb8c4,0x39cbbb99,0x3913378b,0x39cb3732,0x3a2fbb0e,0x3984bb25,0x2e46bba8,0xb303baf6,0xbbf634a5,0xbbce37e3,
0xba2f3b0e,0xb5c23bfa,0x3913378b,0x3b772cb5,0x3bf6b4a5,0x3a8aba4f,0x2e46bba8,0xb89bb8ec,0x3a6d36d7,0x3af6367c,0x38c4bb3b,0x37e3bb50,
0xb81db9ed,0xba0fb89b,0xbadd395f,0xb93a3a8a,0x30b23b88,0x38ec39cb,0x3beab564,0x3a4fb984,0x33c6bbfe,0xb732bac2,0xbbc3aa48,0xbb253848,
0x3b64361f,0x3bb635c2,0x361fbb64,0x3444bb77,0xbb64b61f,0xbbfab179,0xb61f3b64,0xacb53be2,0x3b64361f,0x3bf1a648,0x361fbb64,0xafd6bbff,
0xbb64b61f,0xbb993303,0xb61f3b64,0x35053bce,0x3bea3564,0x3bff3505,0x30b2bb88,0x2648bb99,0xbbc32a48,0xbac23444,0x33c63bfe,0x38483bb6,
0x3a6db6d7,0x367cba0f,0xb8c4bb3b,0xbb50b93a,0xb81d39ed,0x31793bf1,0x3add395f,0x3be22fd6,0x3bf634a5,0x3bce3444,0xae46bba8,0xb303bbb6,
0xb913378b,0xb5c2393a,0x3a2f3b0e,0x3b773a0f,0xae46bba8,0xb89bbbf1,0xbbf6b4a5,0xba8a2fd6,0x3a2f3b0e,0x3bff3732,0x3913b78b,0xa648bb25,
0x3b8833c6,0x3b253303,0xb564bbc3,0xb732bbce,0xaa483a6d,0x34443b50,0x3bfe38c4,0x3bb6367c,0xbb3bbadd,0xbbfab89b,0xb6d7381d,0x2cb53a8a,
0x39edb0b2,0x2fd6b984,0xb95fbbea,0xbbf1b9cb,0x3aa7323e,0x3a0f3179,0xb872bbd9,0xb93abbe2,0x38723bd9,0x3a4f3bff,0x3aa7323e,0x38eca648,
0xbaa7b23e,0xb7323303,0x38723bd9,0x3b253bce,0xb872bbd9,0xbbb6bb50,0xbaa7b23e,0xb444367c,0x395f30b2,0x389b2fd6,0xb9edbbea,0xba8abbf1,
0x3b883bc3,0x3bff3b25,0x3564b3c6,0x2648b732,0x2a4838c4,0x38483af6,0x3bfe3a6d,0x3ac237e3,0xbb3bb81d,0xb67c2cb5,0x36d73add,0x3b503bfa,
0x378b2e46,0x35c22cb5,0xbb0ebbf6,0xbb77bbfa,0x3ba83a2f,0x3a8a38ec,0xb4a5b913,0xb89bba4f,0x3b0e3bf6,0x3bff3b99,0x378b2e46,0xa648b505,
0x34a53913,0x3ac23bb6,0x3ba83a2f,0x38483444,0x33c62a48,0x2fd62648,0xbbc3bbfe,0xbbf1bbff,0x38c436d7,0x35053303,0xba6dbb3b,0xbb99bbce,
0x3add39ed,0x37e3367c,0xb81db95f,0xbaf6bb50,0x3bea3b88,0x393a389b,0xb0b2b564,0xba0fba8a,0x3c003c00,0xbbf1bbff,0,0x2fd62648,
0x3c003c00,0xbb99bbce,0,0x35053303,0x3c003c00,0xbaf6bb50,0,0x37e3367c,0x3c003c00,0xba0fba8a,0,0x393a389b,
0x3bc33bfe,0xbb77bbfa,0xb3c6aa48,0x35c22cb5,0x3a6d3b3b,0xb89bba4f,0xb8c4b6d7,0x3a8a38ec,0x381d395f,0xa648b505,0xbaddb9ed,0x3bff3b99,
0x30b23564,0x38483444,0xbbeabb88,0x3ac23bb6,0x3b0e3bf6,0xba8abbf1,0xb78bae46,0x389b2fd6,0x34a53913,0x2648b732,0xbba8ba2f,0x3bff3b25,
0xb78bae46,0x3ac237e3,0xbb0ebbf6,0x38483af6,0xbba8ba2f,0x3b503bfa,0xb4a5b913,0xb67c2cb5,0x39ed3bea,0xb93abbe2,0xb95fb0b2,0x3a0f3179,
0xb56433c6,0x38eca648,0xbb88bbc3,0x3a4f3bff,0xbbfeba6d,0x3b253bce,0xaa48b8c4,0xb7323303,0xb6d7badd,0xb444367c,0x3b3b381d,0xbbb6bb50,
0x38723bd9,0xb732bbce,0xbaa7b23e,0x3b253303,0xbaa7b23e,0x3bb6367c,0xb872bbd9,0x34443b50,0xb872bbd9,0x2cb53a8a,0x3aa7323e,0xbbfab89b,
0x3aa7323e,0xbbf1b9cb,0x38723bd9,0x2fd6b984,0x35643bc3,0xb303bbb6,0xbb88b3c6,0x3bce3444,0xbbfeb8c4,0x3b773a0f,0x2a48ba6d,0xb5c2393a,
0x36d7b81d,0xba8a2fd6,0x3b3b3add,0xb89bbbf1,0x395f3bea,0xa648bb25,0xb9ed30b2,0x3bff3732,0x2e463ba8,0x2648bb99,0xbbf6b4a5,0x3bff3505,
0xba2fbb0e,0x38483bb6,0x3913b78b,0xbac23444,0x3bf634a5,0xbb50b93a,0x2e463ba8,0x367cba0f,0xb913378b,0x3be22fd6,0xba2fbb0e,0x31793bf1,
0xb0b23b88,0x3444bb77,0xbbeab564,0x3bb635c2,0xb3c6bbfe,0xacb53be2,0x3bc3aa48,0xbbfab179,0x38c43b3b,0xafd6bbff,0xba6d36d7,0x3bf1a648,
0xbaddb95f,0x35053bce,0x381db9ed,0xbb993303,0xb61f3b64,0x37e3bb50,0xbb64b61f,0x3af6367c,0x361fbb64,0xb93a3a8a,0x3b64361f,0xba0fb89b,
0xb61f3b64,0x3a4fb984,0xbb64b61f,0x38ec39cb,0x361fbb64,0xbb253848,0x3b64361f,0xb732bac2,0xb8c43b3b,0x3984bb25,0xba6db6d7,0x39cb3732,
0x3addb95f,0xbbce37e3,0x381d39ed,0xb303baf6,0xbbea3564,0x3b772cb5,0xb0b2bb88,0xb5c23bfa,0x3bc32a48,0xb89bb8ec,0xb3c63bfe,0x3a8aba4f,
0xba2f3b0e,0x3ac2baf6,0xb913b78b,0x384837e3,0x3bf6b4a5,0xbb502cb5,0xae463ba8,0x367cbbfa,0xb913b78b,0x31793a4f,0x3a2fbb0e,0xbbe238ec,
0xae463ba8,0x39cbbb99,0xbbf634a5,0x39843505,0xbb3b3add,0x3b99bac2,0xb6d7b81d,0x35053848,0x39ed30b2,0xb7e3b5c2,0xb95f3bea,0x3af6bb77,
0x3564bbc3,0xba0f3be2,0x3b88b3c6,0xb93ab179,0xbbfe38c4,0x3a4fa648,0xaa48ba6d,0xb8ec3bff,0xbbd93aa7,0x3bfaba8a,0xb23eb872,0x2cb5389b,
0x323e3872,0x2fd6b9cb,0xbbd93aa7,0x3bf1b984,0x3bd9baa7,0xbb993848,0x323e3872,0x3505bac2,0xb23eb872,0xb7e33b77,0x3bd9baa7,0xbaf635c2,
0xbbfe3a6d,0x3be2ba4f,0x2a48b8c4,0xb17938ec,0xb6d73add,0x3984bb99,0xbb3b381d,0x39cbb505,0x395fb0b2,0xb303b444,0xb9ed3bea,0x3bcebbb6,
0x3b88bbc3,0xbb77393a,0x356433c6,0x35c2ba0f,0xbba83a2f,0x3b50ba0f,0x34a5b913,0xb67c393a,0xbb0e3bf6,0x3be2bbf1,0xb78b2e46,0x31792fd6,
0xb4a53913,0x39cbbb25,0xbba83a2f,0x3984b732,0x378bae46,0x3303b7e3,0xbb0e3bf6,0x3bcebaf6,0xbadd39ed,0x3a4fb9cb,0x381db95f,0xb8ec3984,
0xbbea3b88,0x3b25bac2,0x30b2b564,0xb7323848,0xbbc33bfe,0x3bb6bb77,0xb3c62a48,0xb44435c2,0xba6d3b3b,0x3bfabbe2,0xb8c436d7,0xacb53179,
0xb9a839a8,0x38ecb984,0x39a8b9a8,0xba4f39cb,0xb9a839a8,0x3732b848,0x39a8b9a8,0xbb253ac2,0xb9a839a8,0x3444b5c2,0x39a8b9a8,0xbbb63b77,
0xb9a839a8,0x2cb5b179,0x39a8b9a8,0xbbfa3be2,0xb81d395f,0x367cb93a,0x3addb9ed,0xbb503a0f,0xb0b23564,0xb179afd6,0x3beabb88,0xbbe23bf1,
0x33c6aa48,0xb9843732,0x3bc3bbfe,0xb9cb3b25,0x38c4b6d7,0xbbce3af6,0x3a6dbb3b,0xb30337e3,0xb4a53913,0x3179b8ec,0x3ba8ba2f,0xbbe23a4f,
0x378bae46,0xb9cb3505,0x3b0ebbf6,0xb9843b99,0x3ba8ba2f,0xbbce3bb6,0x34a5b913,0x33033444,0x3b0ebbf6,0xb5c23a0f,0xb78b2e46,0x3b77b93a,
0xaa4838c4,0xacb5b89b,0x3bfeba6d,0xbbfa3a8a,0x3b3bb81d,0xbbf13984,0x36d7badd,0xafd639cb,0x39edbbea,0xb5053ac2,0xb95f30b2,0x3b99b848,
0xb564b3c6,0x3af6b5c2,0xbb883bc3,0x37e3bb77,0x323e3872,0xb505b848,0x3bd9baa7,0xbb993ac2,0x3bd9baa7,0xbaf63b77,0xb23eb872,0x37e335c2,
0xb23eb872,0x393a3179,0xbbd93aa7,0x3a0fbbe2,0xbbd93aa7,0x38ecbbff,0x323e3872,0xba4f2648,0x36d7381d,0xb848b7e3,0x3b3bbadd,0xbac23af6,
0x395fbbea,0xb67c3bfa,0xb9edb0b2,0x3b50acb5,0xbb8833c6,0x3be2b8ec,0xb5643bc3,0xb179ba4f,0x2a483a6d,0xb984b505,0x3bfeb8c4,0xb9cb3b99,
0x3913378b,0xb9cbb732,0x3a2fbb0e,0xb9843b25,0x2e46bba8,0x33033af6,0xbbf634a5,0x3bceb7e3,0xba2f3b0e,0x35c2bbfa,0x3913378b,0xbb77acb5,
0x3bf6b4a5,0xba8a3a4f,0x2e46bba8,0x389b38ec,0x3a6d36d7,0xbaf6b67c,0x38c4bb3b,0xb7e33b50,0xb81db9ed,0x3a0f389b,0xbadd395f,0x393aba8a,
0x30b23b88,0xb8ecb9cb,0x3beab564,0xba4f3984,0x33c6bbfe,0x37323ac2,0xbbc3aa48,0x3b25b848,0x3b64361f,0xbbb6b5c2,0x361fbb64,0xb4443b77,
0xbb64b61f,0x3bfa3179,0xb61f3b64,0x2cb5bbe2,0x3b64361f,0xbbf12648,0x361fbb64,0x2fd63bff,0xbb64b61f,0x3b99b303,0xb61f3b64,0xb505bbce,
0x3bea3564,0xbbffb505,0x30b2bb88,0xa6483b99,0xbbc32a48,0x3ac2b444,0x33c63bfe,0xb848bbb6,0x3a6db6d7,0xb67c3a0f,0xb8c4bb3b,0x3b50393a,
0xb81d39ed,0xb179bbf1,0x3add395f,0xbbe2afd6,0x3bf634a5,0xbbceb444,0xae46bba8,0x33033bb6,0xb913378b,0x35c2b93a,0x3a2f3b0e,0xbb77ba0f,
0xae46bba8,0x389b3bf1,0xbbf6b4a5,0x3a8aafd6,0x3a2f3b0e,0xbbffb732,0x3913b78b,0x26483b25,0x3b8833c6,0xbb25b303,0xb564bbc3,0x37323bce,
0xaa483a6d,0xb444bb50,0x3bfe38c4,0xbbb6b67c,0xbb3bbadd,0x3bfa389b,0xb6d7381d,0xacb5ba8a,0x39edb0b2,0xafd63984,0xb95fbbea,0x3bf139cb,
0x3aa7323e,0xba0fb179,0xb872bbd9,0x393a3be2,0x38723bd9,0xba4fbbff,0x3aa7323e,0xb8ec2648,0xbaa7b23e,0x3732b303,0x38723bd9,0xbb25bbce,
0xb872bbd9,0x3bb63b50,0xbaa7b23e,0x3444b67c,0x395f30b2,0xb89bafd6,0xb9edbbea,0x3a8a3bf1,0x3b883bc3,0xbbffbb25,0x3564b3c6,0xa6483732,
0x2a4838c4,0xb848baf6,0x3bfe3a6d,0xbac2b7e3,0xbb3bb81d,0x367cacb5,0x36d73add,0xbb50bbfa,0x378b2e46,0xb5c2acb5,0xbb0ebbf6,0x3b773bfa,
0x3ba83a2f,0xba8ab8ec,0xb4a5b913,0x389b3a4f,0x3b0e3bf6,0xbbffbb99,0x378b2e46,0x26483505,0x34a53913,0xbac2bbb6,0x3ba83a2f,0xb848b444,
0x33c62a48,0xafd6a648,0xbbc3bbfe,0x3bf13bff,0x38c436d7,0xb505b303,0xba6dbb3b,0x3b993bce,0x3add39ed,0xb7e3b67c,0xb81db95f,0x3af63b50,
0x3bea3b88,0xb93ab89b,0xb0b2b564,0x3a0f3a8a,0x3c003c00,0x38ec3984,0,0xba4fb9cb,0x3c003c00,0x37323848,0,0xbb25bac2,
0x3c003c00,0x344435c2,0,0xbbb6bb77,0x3c003c00,0x2cb53179,0,0xbbfabbe2,0xb3c6aa48,0xbb50ba0f,0xbbc3bbfe,0xb67cb93a,
0xb8c4b6d7,0xbbe2bbf1,0xba6dbb3b,0x3179afd6,0xbaddb9ed,0xb9cbbb25,0xb81db95f,0x39843732,0xbbeabb88,0xb303b7e3,0xb0b2b564,0x3bce3af6,
0xbb0ebbf6,0xb179b8ec,0x378b2e46,0x3be23a4f,0xb4a5b913,0x39cb3505,0x3ba83a2f,0x39843b99,0x378b2e46,0x3bce3bb6,0x3b0e3bf6,0xb3033444,
0x3ba83a2f,0x35c23a0f,0x34a53913,0xbb77b93a,0x395f30b2,0x3bfa3a8a,0x39ed3bea,0xacb5389b,0x3b883bc3,0x2fd639cb,0xb56433c6,0xbbf1b984,
0x2a4838c4,0xbb99b848,0xbbfeba6d,0xb505bac2,0xbb3bb81d,0xb7e3bb77,0xb6d7badd,0x3af635c2,0x38723bd9,0xb5053848,0xbaa7b23e,0xbb99bac2,
0xbaa7b23e,0xbaf6bb77,0xb872bbd9,0x37e3b5c2,0xb872bbd9,0x393ab179,0x3aa7323e,0x3a0f3be2,0x3aa7323e,0x38ec3bff,0x38723bd9,0xba4fa648,
0xbb88b3c6,0xbac2baf6,0xb564bbc3,0x3848b7e3,0x2a48ba6d,0x3b502cb5,0x3bfe38c4,0x367c3bfa,0x3b3b3add,0xb1793a4f,0xb6d7381d,0xbbe2b8ec,
0xb9ed30b2,0xb9cbbb99,0xb95fbbea,0x3984b505,0xae46bba8,0x39cbb732,0x3bf634a5,0x39843b25,0x3a2f3b0e,0xb3033af6,0xb913378b,0xbbceb7e3,
0xbbf6b4a5,0xb5c2bbfa,0xae46bba8,0x3b77acb5,0x3913b78b,0x3a8a3a4f,0x3a2f3b0e,0xb89b38ec,0x3bea3564,0x37e33b50,0xb0b23b88,0xbaf6367c,
0xbbc32a48,0xb93aba8a,0xb3c6bbfe,0x3a0fb89b,0x3a6db6d7,0x3a4f3984,0x38c43b3b,0xb8ec39cb,0xb81d39ed,0xbb25b848,0xbaddb95f,0x3732bac2,
0xb61f3b64,0xbbb635c2,0xbb64b61f,0xb444bb77,0x361fbb64,0x3bfab179,0x3b64361f,0x2cb53be2,0xb61f3b64,0xbbf1a648,0xbb64b61f,0x2fd6bbff,
0x361fbb64,0x3b993303,0x3b64361f,0xb5053bce,0xba6db6d7,0xa648bb99,0x38c4bb3b,0x3bffb505,0x381d39ed,0xb8483bb6,0xbadd395f,0xbac2b444,
0xb0b2bb88,0x3b50b93a,0x3beab564,0x367c3a0f,0xb3c63bfe,0xbbe22fd6,0xbbc3aa48,0x3179bbf1,0x3a2fbb0e,0x3bceb444,0x3913378b,0xb3033bb6,
0xbbf634a5,0xb5c2b93a,0x2e46bba8,0x3b77ba0f,0x3913378b,0xb89b3bf1,0xba2f3b0e,0xba8aafd6,0x2e46bba8,0x3bffb732,0x3bf6b4a5,0xa6483b25,
0x36d7381d,0xb7323bce,0xbb3b3add,0xbb253303,0x395fbbea,0x3bb6b67c,0x39ed30b2,0xb4443b50,0xbb8833c6,0x2cb5ba8a,0x3564bbc3,0x3bfab89b,
0x2a483a6d,0xbbf139cb,0xbbfe38c4,0xafd6b984,0xbbd93aa7,0xba0f3179,0xb23eb872,0x393abbe2,0x323e3872,0xba4f3bff,0xbbd93aa7,0xb8eca648,
0x3bd9baa7,0x37323303,0x323e3872,0xbb253bce,0xb23eb872,0x3bb6bb50,0x3bd9baa7,0x3444367c,0x2a48b8c4,0x3a8abbf1,0x3bfeba6d,0x389bafd6,
0xbb3b381d,0xa648b732,0x36d7badd,0x3bffbb25,0xb9ed3bea,0xbac237e3,0xb95f30b2,0x3848baf6,0x356433c6,0xbb503bfa,0xbb883bc3,0xb67cacb5,
0x3ba8ba2f,0x35c2acb5,0xb4a53913,0xbb773bfa,0x3b0ebbf6,0x3a8ab8ec,0x378bae46,0xb89b3a4f,0x34a5b913,0x3bffbb99,0x3ba8ba2f,0xa6483505,
0xb78b2e46,0x3ac2bbb6,0x3b0ebbf6,0x3848b444,0xb81d395f,0xbbf13bff,0xbadd39ed,0xafd62648,0xb0b23564,0xbb993bce,0xbbea3b88,0xb5053303,
0x33c6aa48,0xbaf63b50,0xbbc33bfe,0xb7e3367c,0x38c4b6d7,0xba0f3a8a,0xba6d3b3b,0xb93a389b,0xb9a839a8,0x2fd6a648,0x39a8b9a8,0x3bf1bbff,
0xb9a839a8,0x3505b303,0x39a8b9a8,0x3b99bbce,0xb9a839a8,0x37e3b67c,0x39a8b9a8,0x3af6bb50,0xb9a839a8,0x393ab89b,0x39a8b9a8,0x3a0fba8a,
0x3addb9ed,0x3b77bbfa,0x381db95f,0xb5c22cb5,0x3beabb88,0x389bba4f,0x30b2b564,0xba8a38ec,0x3bc3bbfe,0x2648b505,0xb3c62a48,0xbbff3b99,
0x3a6dbb3b,0xb8483444,0xb8c436d7,0xbac23bb6,0x34a5b913,0xb89b2fd6,0xbba83a2f,0xba8a3bf1,0xb78b2e46,0xbbff3b25,0xbb0e3bf6,0x26483732,
0xbba83a2f,0xb8483af6,0xb4a53913,0x3ac2b7e3,0xbb0e3bf6,0x367c2cb5,0x378bae46,0x3b50bbfa,0xbbfe3a6d,0xb93a3be2,0xaa4838c4,0x3a0fb179,
0xb6d73add,0x38ec2648,0x3b3bb81d,0x3a4fbbff,0x395fb0b2,0x3b25bbce,0x39edbbea,0xb732b303,0x3b88bbc3,0xb444b67c,0xb564b3c6,0xbbb63b50,
0x323e3872,0x3b25b303,0x3bd9baa7,0x3732bbce,0x3bd9baa7,0x3444bb50,0xb23eb872,0xbbb6367c,0xb23eb872,0xbbfa389b,0xbbd93aa7,0xacb53a8a,
0xbbd93aa7,0x2fd63984,0x323e3872,0x3bf1b9cb,0x3b3bbadd,0x3303bbb6,0xb6d7b81d,0xbbce3444,0xb9edb0b2,0xbb773a0f,0xb95f3bea,0x35c2393a,
0xb5643bc3,0x3a8a2fd6,0x3b88b3c6,0x389bbbf1,0x3bfeb8c4,0x2648bb25,0xaa48ba6d,0xbbff3732,0xb913b78b,0xbbff3505,0xba2f3b0e,0x26483b99,
0xae463ba8,0x3ac23444,0x3bf6b4a5,0x3848bbb6,0x3a2fbb0e,0xb67cba0f,0xb913b78b,0xbb50393a,0xbbf634a5,0xb1793bf1,0xae463ba8,0x3be2afd6,
0xb8c43b3b,0x34443b77,0x3a6d36d7,0x3bb6b5c2,0x3addb95f,0xacb5bbe2,0xb81db9ed,0xbbfa3179,0xbbea3564,0xafd63bff,0x30b23b88,0x3bf12648,
0x3bc32a48,0x3505bbce,0x33c6bbfe,0xbb99b303,0x3b64361f,0x3af6b67c,0x361fbb64,0xb7e3bb50,0xbb64b61f,0xba0f389b,0xb61f3b64,0x393a3a8a,
0x3b64361f,0x38ecb9cb,0x361fbb64,0xba4fb984,0xbb64b61f,0xb7323ac2,0xb61f3b64,0x3b253848,0x30b2bb88,0xb984bb25,0xbbeab564,0xb9cb3732,
0x33c63bfe,0x3bce37e3,0x3bc3aa48,0x3303baf6,0xb8c4bb3b,0xbb772cb5,0xba6d36d7,0x35c23bfa,0x3add395f,0x389bb8ec,0x381db9ed,0xba8aba4f,
0xbbf6b4a5,0xb84837e3,0x2e463ba8,0x3ac23af6,0x3913b78b,0xb67cbbfa,0xba2fbb0e,0xbb50acb5,0x2e463ba8,0x3be238ec,0x3bf634a5,0x3179ba4f,
0xba2fbb0e,0xb9843505,0xb913378b,0x39cb3b99,0x35643bc3,0x3b993ac2,0x3b8833c6,0x3505b848,0xbbfeb8c4,0xb7e335c2,0xaa483a6d,0x3af63b77,
0x36d7b81d,0xba0fbbe2,0xbb3bbadd,0xb93a3179,0x395f3bea,0x3a4f2648,0x39edb0b2,0xb8ecbbff,0x3aa7323e,0x2cb5b89b,0xb872bbd9,0xbbfaba8a,
0x38723bd9,0x3bf13984,0x3aa7323e,0xafd6b9cb,0xbaa7b23e,0x35053ac2,0x38723bd9,0x3b993848,0xb872bbd9,0xbaf6b5c2,0xbaa7b23e,0x37e33b77,
0xb9edbbea,0xbbe2ba4f,0xb95fb0b2,0x317938ec,0x3564b3c6,0xb984bb99,0xbb88bbc3,0xb9cbb505,0x3bfe3a6d,0x3303b444,0xaa48b8c4,0xbbcebbb6,
0x36d73add,0x3b77393a,0x3b3b381d,0xb5c2ba0f,0xb78bae46,0x367c393a,0x3b0e3bf6,0x3b503a0f,0xbba8ba2f,0xb1792fd6,0x34a53913,0x3be23bf1,
0xbb0ebbf6,0xb984b732,0xb78bae46,0x39cb3b25,0xb4a5b913,0xbbcebaf6,0xbba8ba2f,0x330337e3,0x3bc33bfe,0x3a4f39cb,0x33c62a48,0xb8ecb984,
0x3a6d3b3b,0x3b253ac2,0x38c436d7,0xb732b848,0x381d395f,0x3bb63b77,0x3add39ed,0xb444b5c2,0x30b23564,0x3bfa3be2,0x3bea3b88,0xacb5b179,
0x3c003c00,0xb8ecb984,0,0x3a4f39cb,0x3c003c00,0xb732b848,0,0x3b253ac2,0x3c003c00,0xb444b5c2,0,0x3bb63b77,
0x3c003c00,0xacb5b179,0,0x3bfa3be2,0xb3c6aa48,0x3b503a0f,0xbbc3bbfe,0x367c393a,0xb8c4b6d7,0x3be23bf1,0xba6dbb3b,0xb1792fd6,
0xbaddb9ed,0x39cb3b25,0xb81db95f,0xb984b732,0xbbeabb88,0x330337e3,0xb0b2b564,0xbbcebaf6,0xbb0ebbf6,0x317938ec,0x378b2e46,0xbbe2ba4f,
0xb4a5b913,0xb9cbb505,0x3ba83a2f,0xb984bb99,0x378b2e46,0xbbcebbb6,0x3b0e3bf6,0x3303b444,0x3ba83a2f,0xb5c2ba0f,0x34a53913,0x3b77393a,
0x395f30b2,0xbbfaba8a,0x39ed3bea,0x2cb5b89b,0x3b883bc3,0xafd6b9cb,0xb56433c6,0x3bf13984,0x2a4838c4,0x3b993848,0xbbfeba6d,0x35053ac2,
0xbb3bb81d,0x37e33b77,0xb6d7badd,0xbaf6b5c2,0x38723bd9,0x3505b848,0xbaa7b23e,0x3b993ac2,0xbaa7b23e,0x3af63b77,0xb872bbd9,0xb7e335c2,
0xb872bbd9,0xb93a3179,0x3aa7323e,0xba0fbbe2,0x3aa7323e,0xb8ecbbff,0x38723bd9,0x3a4f2648,0xbb88b3c6,0x3ac23af6,0xb564bbc3,0xb84837e3,
0x2a48ba6d,0xbb50acb5,0x3bfe38c4,0xb67cbbfa,0x3b3b3add,0x3179ba4f,0xb6d7381d,0x3be238ec,0xb9ed30b2,0x39cb3b99,0xb95fbbea,0xb9843505,
0xae46bba8,0xb9cb3732,0x3bf634a5,0xb984bb25,0x3a2f3b0e,0x3303baf6,0xb913378b,0x3bce37e3,0xbbf6b4a5,0x35c23bfa,0xae46bba8,0xbb772cb5,
0x3913b78b,0xba8aba4f,0x3a2f3b0e,0x389bb8ec,0x3bea3564,0xb7e3bb50,0xb0b23b88,0x3af6b67c,0xbbc32a48,0x393a3a8a,0xb3c6bbfe,0xba0f389b,
0x3a6db6d7,0xba4fb984,0x38c43b3b,0x38ecb9cb,0xb81d39ed,0x3b253848,0xbaddb95f,0xb7323ac2,0xb61f3b64,0x3bb6b5c2,0xbb64b61f,0x34443b77,
0x361fbb64,0xbbfa3179,0x3b64361f,0xacb5bbe2,0xb61f3b64,0x3bf12648,0xbb64b61f,0xafd63bff,0x361fbb64,0xbb99b303,0x3b64361f,0x3505bbce,
0xba6db6d7,0x26483b99,0x38c4bb3b,0xbbff3505,0x381d39ed,0x3848bbb6,0xbadd395f,0x3ac23444,0xb0b2bb88,0xbb50393a,0x3beab564,0xb67cba0f,
0xb3c63bfe,0x3be2afd6,0xbbc3aa48,0xb1793bf1,0x3a2fbb0e,0xbbce3444,0x3913378b,0x3303bbb6,0xbbf634a5,0x35c2393a,0x2e46bba8,0xbb773a0f,
0x3913378b,0x389bbbf1,0xba2f3b0e,0x3a8a2fd6,0x2e46bba8,0xbbff3732,0x3bf6b4a5,0x2648bb25,0x36d7381d,0x3732bbce,0xbb3b3add,0x3b25b303,
0x395fbbea,0xbbb6367c,0x39ed30b2,0x3444bb50,0xbb8833c6,0xacb53a8a,0x3564bbc3,0xbbfa389b,0x2a483a6d,0x3bf1b9cb,0xbbfe38c4,0x2fd63984,
0xbbd93aa7,0x3a0fb179,0xb23eb872,0xb93a3be2,0x323e3872,0x3a4fbbff,0xbbd93aa7,0x38ec2648,0x3bd9baa7,0xb732b303,0x323e3872,0x3b25bbce,
0xb23eb872,0xbbb63b50,0x3bd9baa7,0xb444b67c,0x2a48b8c4,0xba8a3bf1,0x3bfeba6d,0xb89b2fd6,0xbb3b381d,0x26483732,0x36d7badd,0xbbff3b25,
0xb9ed3bea,0x3ac2b7e3,0xb95f30b2,0xb8483af6,0x356433c6,0x3b50bbfa,0xbb883bc3,0x367c2cb5,0x3ba8ba2f,0xb5c22cb5,0xb4a53913,0x3b77bbfa,
0x3b0ebbf6,0xba8a38ec,0x378bae46,0x389bba4f,0x34a5b913,0xbbff3b99,0x3ba8ba2f,0x2648b505,0xb78b2e46,0xbac23bb6,0x3b0ebbf6,0xb8483444,
0xb81d395f,0x3bf1bbff,0xbadd39ed,0x2fd6a648,0xb0b23564,0x3b99bbce,0xbbea3b88,0x3505b303,0x33c6aa48,0x3af6bb50,0xbbc33bfe,0x37e3b67c,
0x38c4b6d7,0x3a0fba8a,0xba6d3b3b,0x393ab89b,0xb9a839a8,0xafd62648,0x39a8b9a8,0xbbf13bff,0xb9a839a8,0xb5053303,0x39a8b9a8,0xbb993bce,
0xb9a839a8,0xb7e3367c,0x39a8b9a8,0xbaf63b50,0xb9a839a8,0xb93a389b,0x39a8b9a8,0xba0f3a8a,0x3addb9ed,0xbb773bfa,0x381db95f,0x35c2acb5,
0x3beabb88,0xb89b3a4f,0x30b2b564,0x3a8ab8ec,0x3bc3bbfe,0xa6483505,0xb3c62a48,0x3bffbb99,0x3a6dbb3b,0x3848b444,0xb8c436d7,0x3ac2bbb6,
0x34a5b913,0x389bafd6,0xbba83a2f,0x3a8abbf1,0xb78b2e46,0x3bffbb25,0xbb0e3bf6,0xa648b732,0xbba83a2f,0x3848baf6,0xb4a53913,0xbac237e3,
0xbb0e3bf6,0xb67cacb5,0x378bae46,0xbb503bfa,0xbbfe3a6d,0x393abbe2,0xaa4838c4,0xba0f3179,0xb6d73add,0xb8eca648,0x3b3bb81d,0xba4f3bff,
0x395fb0b2,0xbb253bce,0x39edbbea,0x37323303,0x3b88bbc3,0x3444367c,0xb564b3c6,0x3bb6bb50,0x323e3872,0xbb253303,0x3bd9baa7,0xb7323bce,
0x3bd9baa7,0xb4443b50,0xb23eb872,0x3bb6b67c,0xb23eb872,0x3bfab89b,0xbbd93aa7,0x2cb5ba8a,0xbbd93aa7,0xafd6b984,0x323e3872,0xbbf139cb,
0x3b3bbadd,0xb3033bb6,0xb6d7b81d,0x3bceb444,0xb9edb0b2,0x3b77ba0f,0xb95f3bea,0xb5c2b93a,0xb5643bc3,0xba8aafd6,0x3b88b3c6,0xb89b3bf1,
0x3bfeb8c4,0xa6483b25,0xaa48ba6d,0x3bffb732,0xb913b78b,0x3bffb505,0xba2f3b0e,0xa648bb99,0xae463ba8,0xbac2b444,0x3bf6b4a5,0xb8483bb6,
0x3a2fbb0e,0x367c3a0f,0xb913b78b,0x3b50b93a,0xbbf634a5,0x3179bbf1,0xae463ba8,0xbbe22fd6,0xb8c43b3b,0xb444bb77,0x3a6d36d7,0xbbb635c2,
0x3addb95f,0x2cb53be2,0xb81db9ed,0x3bfab179,0xbbea3564,0x2fd6bbff,0x30b23b88,0xbbf1a648,0x3bc32a48,0xb5053bce,0x33c6bbfe,0x3b993303,
0x3b64361f,0xbaf6367c,0x361fbb64,0x37e33b50,0xbb64b61f,0x3a0fb89b,0xb61f3b64,0xb93aba8a,0x3b64361f,0xb8ec39cb,0x361fbb64,0x3a4f3984,
0xbb64b61f,0x3732bac2,0xb61f3b64,0xbb25b848,0x30b2bb88,0x39843b25,0xbbeab564,0x39cbb732,0x33c63bfe,0xbbceb7e3,0x3bc3aa48,0xb3033af6,
0xb8c4bb3b,0x3b77acb5,0xba6d36d7,0xb5c2bbfa,0x3add395f,0xb89b38ec,0x381db9ed,0x3a8a3a4f,0xbbf6b4a5,0x3848b7e3,0x2e463ba8,0xbac2baf6,
0x3913b78b,0x367c3bfa,0xba2fbb0e,0x3b502cb5,0x2e463ba8,0xbbe2b8ec,0x3bf634a5,0xb1793a4f,0xba2fbb0e,0x3984b505,0xb913378b,0xb9cbbb99,
0x35643bc3,0xbb99bac2,0x3b8833c6,0xb5053848,0xbbfeb8c4,0x37e3b5c2,0xaa483a6d,0xbaf6bb77,0x36d7b81d,0x3a0f3be2,0xbb3bbadd,0x393ab179,
0x395f3bea,0xba4fa648,0x39edb0b2,0x38ec3bff,0x3aa7323e,0xacb5389b,0xb872bbd9,0x3bfa3a8a,0x38723bd9,0xbbf1b984,0x3aa7323e,0x2fd639cb,
0xbaa7b23e,0xb505bac2,0x38723bd9,0xbb99b848,0xb872bbd9,0x3af635c2,0xbaa7b23e,0xb7e3bb77,0xb9edbbea,0x3be23a4f,0xb95fb0b2,0xb179b8ec,
0x3564b3c6,0x39843b99,0xbb88bbc3,0x39cb3505,0x3bfe3a6d,0xb3033444,0xaa48b8c4,0x3bce3bb6,0x36d73add,0xbb77b93a,0x3b3b381d,0x35c23a0f,
0xb78bae46,0xb67cb93a,0x3b0e3bf6,0xbb50ba0f,0xbba8ba2f,0x3179afd6,0x34a53913,0xbbe2bbf1,0xbb0ebbf6,0x39843732,0xb78bae46,0xb9cbbb25,
0xb4a5b913,0x3bce3af6,0xbba8ba2f,0xb303b7e3,0x3bc33bfe,0xba4fb9cb,0x33c62a48,0x38ec3984,0x3a6d3b3b,0xbb25bac2,0x38c436d7,0x37323848,
0x381d395f,0xbbb6bb77,0x3add39ed,0x344435c2,0x30b23564,0xbbfabbe2,0x3bea3b88,0x2cb53179,0x3c003c00,0xafd6a648,0,0xbbf1bbff,
0x3c003c00,0xb505b303,0,0xbb99bbce,0x3c003c00,0xb7e3b67c,0,0xbaf6bb50,0x3c003c00,0xb93ab89b,0,0xba0fba8a,
0xbbc3bbfe,0x35c22cb5,0x33c62a48,0x3b773bfa,0xba6dbb3b,0x3a8a38ec,0x38c436d7,0x389b3a4f,0xb81db95f,0x3bff3b99,0x3add39ed,0x26483505,
0xb0b2b564,0x3ac23bb6,0x3bea3b88,0xb848b444,0x3b0e3bf6,0xb89bafd6,0xb78bae46,0xba8abbf1,0x34a53913,0xbbffbb25,0xbba8ba2f,0x2648b732,
0xb78bae46,0xb848baf6,0xbb0ebbf6,0x3ac237e3,0xbba8ba2f,0x367cacb5,0xb4a5b913,0x3b503bfa,0xb9edbbea,0x3a0f3179,0x395f30b2,0x393a3be2,
0x3564b3c6,0x3a4f3bff,0x3b883bc3,0xb8ec2648,0x3bfe3a6d,0xb7323303,0x2a4838c4,0xbb25bbce,0x36d73add,0xbbb6bb50,0xbb3bb81d,0x3444b67c,
0x38723bd9,0xbb25b303,0xbaa7b23e,0xb732bbce,0xbaa7b23e,0xb444bb50,0xb872bbd9,0x3bb6367c,0xb872bbd9,0x3bfa389b,0x3aa7323e,0x2cb53a8a,
0x3aa7323e,0xafd63984,0x38723bd9,0xbbf1b9cb,0xb564bbc3,0x3bce3444,0x3b8833c6,0x33033bb6,0x3bfe38c4,0xb5c2393a,0xaa483a6d,0xbb77ba0f,
0xb6d7381d,0xb89bbbf1,0xbb3bbadd,0x3a8aafd6,0xb95fbbea,0x3bff3732,0x39edb0b2,0x26483b25,0x2e463ba8,0xbbffb505,0xbbf6b4a5,0x2648bb99,
0xba2fbb0e,0x3ac2b444,0x3913b78b,0x38483bb6,0x3bf634a5,0xb67c3a0f,0x2e463ba8,0xbb50b93a,0xb913378b,0xb179bbf1,0xba2fbb0e,0x3be22fd6,
0x30b2bb88,0x3bb635c2,0x3bea3564,0xb4443b77,0x33c63bfe,0xbbfab179,0xbbc32a48,0x2cb5bbe2,0xb8c4bb3b,0x3bf1a648,0x3a6db6d7,0x2fd63bff,
0x3add395f,0xbb993303,0xb81d39ed,0xb505bbce,0xb61f3b64,0xbaf6b67c,0xbb64b61f,0x37e3bb50,0x361fbb64,0x3a0f389b,0x3b64361f,0xb93a3a8a,
0xb61f3b64,0xb8ecb9cb,0xbb64b61f,0x3a4fb984,0x361fbb64,0x37323ac2,0x3b64361f,0xbb253848,0x38c4bb3b,0x39cb3732,0x3a6d36d7,0xb9843b25,
0xbadd395f,0xb303baf6,0xb81db9ed,0x3bceb7e3,0x3beab564,0xb5c23bfa,0x30b23b88,0xbb77acb5,0xbbc3aa48,0x3a8aba4f,0x33c6bbfe,0x389b38ec,
0xba2f3b0e,0xb848b7e3,0xb913b78b,0x3ac2baf6,0x3bf6b4a5,0xb67c3bfa,0xae463ba8,0xbb502cb5,0xb913b78b,0x3be2b8ec,0x3a2fbb0e,0x31793a4f,
0xae463ba8,0xb984b505,0xbbf634a5,0x39cbbb99,0x3b3bbadd,0x35053848,0x36d7381d,0xbb993ac2,0xb9edb0b2,0x3af6bb77,0x395fbbea,0x37e335c2,
0xb5643bc3,0xb93ab179,0xbb8833c6,0x3a0fbbe2,0x3bfeb8c4,0xb8ec3bff,0x2a483a6d,0xba4f2648,0xbbd93aa7,0xacb5b89b,0xb23eb872,0x3bfaba8a,
0x323e3872,0xbbf13984,0xbbd93aa7,0x2fd6b9cb,0x3bd9baa7,0xb5053ac2,0x323e3872,0xbb993848,0xb23eb872,0x3af6b5c2,0x3bd9baa7,0xb7e33b77,
0x3bfeba6d,0xb17938ec,0xaa4838c4,0xbbe23a4f,0x36d7badd,0x39cbb505,0x3b3bb81d,0xb9843b99,0xb95f30b2,0x3bcebbb6,0x39edbbea,0x33033444,
0xbb883bc3,0x35c2ba0f,0xb564b3c6,0x3b77b93a,0xbba83a2f,0x367cb93a,0x34a5b913,0x3b50ba0f,0xbb0e3bf6,0xb179afd6,0xb78b2e46,0x3be2bbf1,
0xb4a53913,0xb9843732,0xbba83a2f,0x39cbbb25,0x378bae46,0xbbce3af6,0xbb0e3bf6,0x3303b7e3,0x3addb9ed,0xb8ec3984,0xb81d395f,0xba4f39cb,
0x3beabb88,0xb7323848,0xb0b23564,0xbb253ac2,0x3bc3bbfe,0xb44435c2,0x33c6aa48,0xbbb63b77,0x3a6dbb3b,0xacb53179,0x38c4b6d7,0xbbfa3be2,
0xb9a839a8,0x3a4fb9cb,0x39a8b9a8,0x38ecb984,0xb9a839a8,0x3b25bac2,0x39a8b9a8,0x3732b848,0xb9a839a8,0x3bb6bb77,0x39a8b9a8,0x3444b5c2,
0xb9a839a8,0x3bfabbe2,0x39a8b9a8,0x2cb5b179,0x381db95f,0xbb503a0f,0xbadd39ed,0xb67c393a,0x30b2b564,0xbbe23bf1,0xbbea3b88,0x31792fd6,
0xb3c62a48,0xb9cb3b25,0xbbc33bfe,0x3984b732,0xb8c436d7,0xb30337e3,0xba6d3b3b,0x3bcebaf6,0xb4a53913,0x3be2ba4f,0x3ba8ba2f,0x3179b8ec,
0x378bae46,0x3984bb99,0x3b0ebbf6,0xb9cb3505,0x3ba8ba2f,0xb303b444,0x34a5b913,0xbbce3bb6,0x3b0ebbf6,0xbb77393a,0xb78b2e46,0xb5c23a0f,
0x2a48b8c4,0xbbfa3a8a,0xbbfe3a6d,0x2cb5389b,0xbb3b381d,0xafd639cb,0xb6d73add,0x3bf1b984,0xb9ed3bea,0x3b99b848,0x395fb0b2,0x3505bac2,
0x356433c6,0x37e3bb77,0x3b88bbc3,0xbaf635c2,0x323e3872,0x3b99bac2,0x3bd9baa7,0xb505b848,0x3bd9baa7,0xb7e3b5c2,0xb23eb872,0xbaf63b77,
0xb23eb872,0xba0f3be2,0xbbd93aa7,0x393a3179,0xbbd93aa7,0x3a4fa648,0x323e3872,0x38ecbbff,0xb6d7b81d,0xbac23af6,0xbb3b3add,0x384837e3,
0xb95f3bea,0x3b50acb5,0x39ed30b2,0x367cbbfa,0x3b88b3c6,0xb179ba4f,0x3564bbc3,0xbbe238ec,0xaa48ba6d,0xb9cb3b99,0xbbfe38c4,0x39843505,
0x3913378b,0x3984bb25,0x3a2fbb0e,0xb9cbb732,0x2e46bba8,0xbbce37e3,0xbbf634a5,0x33033af6,0xba2f3b0e,0x3b772cb5,0x3913378b,0x35c2bbfa,
0x3bf6b4a5,0xb89bb8ec,0x2e46bba8,0xba8a3a4f,0xba6db6d7,0xb7e33b50,0xb8c43b3b,0x3af6367c,0x381d39ed,0x393aba8a,0x3addb95f,0xba0fb89b,
0xb0b2bb88,0xba4f3984,0xbbea3564,0x38ec39cb,0xb3c63bfe,0x3b25b848,0x3bc32a48,0xb732bac2,0x3b64361f,0x3444bb77,0x361fbb64,0xbbb6b5c2,
0xbb64b61f,0xacb53be2,0xb61f3b64,0x3bfa3179,0x3b64361f,0xafd6bbff,0x361fbb64,0xbbf12648,0xbb64b61f,0x35053bce,0xb61f3b64,0x3b99b303,
0xbbeab564,0xa6483b99,0xb0b23b88,0x3bff3505,0x3bc3aa48,0xb848bbb6,0xb3c6bbfe,0xbac23444,0xba6d36d7,0x3b50393a,0x38c43b3b,0x367cba0f,
0x381db9ed,0xbbe2afd6,0xbaddb95f,0x31793bf1,0x3bf634a5,0xb303bbb6,0xae46bba8,0xbbceb444,0xb913378b,0x3b773a0f,0x3a2f3b0e,0x35c2b93a,
0xae46bba8,0xba8a2fd6,0xbbf6b4a5,0x389b3bf1,0x3a2f3b0e,0xa648bb25,0x3913b78b,0xbbffb732,0xbb88b3c6,0x37323bce,0x35643bc3,0x3b253303,
0x2a48ba6d,0xbbb6b67c,0xbbfeb8c4,0x34443b50,0x3b3b3add,0xacb5ba8a,0x36d7b81d,0xbbfab89b,0xb9ed30b2,0x3bf139cb,0x395f3bea,0x2fd6b984,
0x3aa7323e,0xb93abbe2,0xb872bbd9,0xba0fb179,0x38723bd9,0x38eca648,0x3aa7323e,0xba4fbbff,0xbaa7b23e,0x3b253bce,0x38723bd9,0x3732b303,
0xb872bbd9,0xb444367c,0xbaa7b23e,0x3bb63b50,0xb95fb0b2,0x3a8a3bf1,0x39ed3bea,0x389b2fd6,0xbb88bbc3,0xa6483732,0xb56433c6,0x3bff3b25,
0xaa48b8c4,0xbac2b7e3,0xbbfeba6d,0x38483af6,0x3b3b381d,0xbb50bbfa,0xb6d7badd,0xb67c2cb5,0x378b2e46,0xbb77bbfa,0xbb0ebbf6,0xb5c2acb5,
0x3ba83a2f,0xb89bba4f,0xb4a5b913,0xba8ab8ec,0x3b0e3bf6,0xa648b505,0x378b2e46,0xbbffbb99,0x34a53913,0x38483444,0x3ba83a2f,0xbac2bbb6,
0xb3c6aa48,0x3bf13bff,0x3bc33bfe,0x2fd62648,0xb8c4b6d7,0x3b993bce,0x3a6d3b3b,0x35053303,0xbaddb9ed,0x3af63b50,0x381d395f,0x37e3367c,
0xbbeabb88,0x3a0f3a8a,0x30b23564,0x393a389b,0x3c003c00,0x2fd62648,0,0x3bf13bff,0x3c003c00,0x35053303,0,0x3b993bce,
0x3c003c00,0x37e3367c,0,0x3af63b50,0x3c003c00,0x393a389b,0,0x3a0f3a8a,0xbbc3bbfe,0xb5c2acb5,0x33c62a48,0xbb77bbfa,
0xba6dbb3b,0xba8ab8ec,0x38c436d7,0xb89bba4f,0xb81db95f,0xbbffbb99,0x3add39ed,0xa648b505,0xb0b2b564,0xbac2bbb6,0x3bea3b88,0x38483444,
0x3b0e3bf6,0x389b2fd6,0xb78bae46,0x3a8a3bf1,0x34a53913,0x3bff3b25,0xbba8ba2f,0xa6483732,0xb78bae46,0x38483af6,0xbb0ebbf6,0xbac2b7e3,
0xbba8ba2f,0xb67c2cb5,0xb4a5b913,0xbb50bbfa,0xb9edbbea,0xba0fb179,0x395f30b2,0xb93abbe2,0x3564b3c6,0xba4fbbff,0x3b883bc3,0x38eca648,
0x3bfe3a6d,0x3732b303,0x2a4838c4,0x3b253bce,0x36d73add,0x3bb63b50,0xbb3bb81d,0xb444367c,0x38723bd9,0x3b253303,0xbaa7b23e,0x37323bce,
0xbaa7b23e,0x34443b50,0xb872bbd9,0xbbb6b67c,0xb872bbd9,0xbbfab89b,0x3aa7323e,0xacb5ba8a,0x3aa7323e,0x2fd6b984,0x38723bd9,0x3bf139cb,
0xb564bbc3,0xbbceb444,0x3b8833c6,0xb303bbb6,0x3bfe38c4,0x35c2b93a,0xaa483a6d,0x3b773a0f,0xb6d7381d,0x389b3bf1,0xbb3bbadd,0xba8a2fd6,
0xb95fbbea,0xbbffb732,0x39edb0b2,0xa648bb25,0x2e463ba8,0x3bff3505,0xbbf6b4a5,0xa6483b99,0xba2fbb0e,0xbac23444,0x3913b78b,0xb848bbb6,
0x3bf634a5,0x367cba0f,0x2e463ba8,0x3b50393a,0xb913378b,0x31793bf1,0xba2fbb0e,0xbbe2afd6,0x30b2bb88,0xbbb6b5c2,0x3bea3564,0x3444bb77,
0x33c63bfe,0x3bfa3179,0xbbc32a48,0xacb53be2,0xb8c4bb3b,0xbbf12648,0x3a6db6d7,0xafd6bbff,0x3add395f,0x3b99b303,0xb81d39ed,0x35053bce,
0xb61f3b64,0x3af6367c,0xbb64b61f,0xb7e33b50,0x361fbb64,0xba0fb89b,0x3b64361f,0x393aba8a,0xb61f3b64,0x38ec39cb,0xbb64b61f,0xba4f3984,
0x361fbb64,0xb732bac2,0x3b64361f,0x3b25b848,0x38c4bb3b,0xb9cbb732,0x3a6d36d7,0x3984bb25,0xbadd395f,0x33033af6,0xb81db9ed,0xbbce37e3,
0x3beab564,0x35c2bbfa,0x30b23b88,0x3b772cb5,0xbbc3aa48,0xba8a3a4f,0x33c6bbfe,0xb89bb8ec,0xba2f3b0e,0x384837e3,0xb913b78b,0xbac23af6,
0x3bf6b4a5,0x367cbbfa,0xae463ba8,0x3b50acb5,0xb913b78b,0xbbe238ec,0x3a2fbb0e,0xb179ba4f,0xae463ba8,0x39843505,0xbbf634a5,0xb9cb3b99,
0x3b3bbadd,0xb505b848,0x36d7381d,0x3b99bac2,0xb9edb0b2,0xbaf63b77,0x395fbbea,0xb7e3b5c2,0xb5643bc3,0x393a3179,0xbb8833c6,0xba0f3be2,
0x3bfeb8c4,0x38ecbbff,0x2a483a6d,0x3a4fa648,0xbbd93aa7,0x2cb5389b,0xb23eb872,0xbbfa3a8a,0x323e3872,0x3bf1b984,0xbbd93aa7,0xafd639cb,
0x3bd9baa7,0x3505bac2,0x323e3872,0x3b99b848,0xb23eb872,0xbaf635c2,0x3bd9baa7,0x37e3bb77,0x3bfeba6d,0x3179b8ec,0xaa4838c4,0x3be2ba4f,
0x36d7badd,0xb9cb3505,0x3b3bb81d,0x3984bb99,0xb95f30b2,0xbbce3bb6,0x39edbbea,0xb303b444,0xbb883bc3,0xb5c23a0f,0xb564b3c6,0xbb77393a,
0xbba83a2f,0xb67c393a,0x34a5b913,0xbb503a0f,0xbb0e3bf6,0x31792fd6,0xb78b2e46,0xbbe23bf1,0xb4a53913,0x3984b732,0xbba83a2f,0xb9cb3b25,
0x378bae46,0x3bcebaf6,0xbb0e3bf6,0xb30337e3,0x3addb9ed,0x38ecb984,0xb81d395f,0x3a4fb9cb,0x3beabb88,0x3732b848,0xb0b23564,0x3b25bac2,
0x3bc3bbfe,0x3444b5c2,0x33c6aa48,0x3bb6bb77,0x3a6dbb3b,0x2cb5b179,0x38c4b6d7,0x3bfabbe2,0xb9a839a8,0xba4f39cb,0x39a8b9a8,0xb8ec3984,
0xb9a839a8,0xbb253ac2,0x39a8b9a8,0xb7323848,0xb9a839a8,0xbbb63b77,0x39a8b9a8,0xb44435c2,0xb9a839a8,0xbbfa3be2,0x39a8b9a8,0xacb53179,
0x381db95f,0x3b50ba0f,0xbadd39ed,0x367cb93a,0x30b2b564,0x3be2bbf1,0xbbea3b88,0xb179afd6,0xb3c62a48,0x39cbbb25,0xbbc33bfe,0xb9843732,
0xb8c436d7,0x3303b7e3,0xba6d3b3b,0xbbce3af6,0xb4a53913,0xbbe23a4f,0x3ba8ba2f,0xb17938ec,0x378bae46,0xb9843b99,0x3b0ebbf6,0x39cbb505,
0x3ba8ba2f,0x33033444,0x34a5b913,0x3bcebbb6,0x3b0ebbf6,0x3b77b93a,0xb78b2e46,0x35c2ba0f,0x2a48b8c4,0x3bfaba8a,0xbbfe3a6d,0xacb5b89b,
0xbb3b381d,0x2fd6b9cb,0xb6d73add,0xbbf13984,0xb9ed3bea,0xbb993848,0x395fb0b2,0xb5053ac2,0x356433c6,0xb7e33b77,0x3b88bbc3,0x3af6b5c2,
0x323e3872,0xbb993ac2,0x3bd9baa7,0x35053848,0x3bd9baa7,0x37e335c2,0xb23eb872,0x3af6bb77,0xb23eb872,0x3a0fbbe2,0xbbd93aa7,0xb93ab179,
0xbbd93aa7,0xba4f2648,0x323e3872,0xb8ec3bff,0xb6d7b81d,0x3ac2baf6,0xbb3b3add,0xb848b7e3,0xb95f3bea,0xbb502cb5,0x39ed30b2,0xb67c3bfa,
0x3b88b3c6,0x31793a4f,0x3564bbc3,0x3be2b8ec,0xaa48ba6d,0x39cbbb99,0xbbfe38c4,0xb984b505,0x3913378b,0xb9843b25,0x3a2fbb0e,0x39cb3732,
0x2e46bba8,0x3bceb7e3,0xbbf634a5,0xb303baf6,0xba2f3b0e,0xbb77acb5,0x3913378b,0xb5c23bfa,0x3bf6b4a5,0x389b38ec,0x2e46bba8,0x3a8aba4f,
0xba6db6d7,0x37e3bb50,0xb8c43b3b,0xbaf6b67c,0x381d39ed,0xb93a3a8a,0x3addb95f,0x3a0f389b,0xb0b2bb88,0x3a4fb984,0xbbea3564,0xb8ecb9cb,
0xb3c63bfe,0xbb253848,0x3bc32a48,0x37323ac2,0x3b64361f,0xb4443b77,0x361fbb64,0x3bb635c2,0xbb64b61f,0x2cb5bbe2,0xb61f3b64,0xbbfab179,
0x3b64361f,0x2fd63bff,0x361fbb64,0x3bf1a648,0xbb64b61f,0xb505bbce,0xb61f3b64,0xbb993303,0xbbeab564,0x2648bb99,0xb0b23b88,0xbbffb505,
0x3bc3aa48,0x38483bb6,0xb3c6bbfe,0x3ac2b444,0xba6d36d7,0xbb50b93a,0x38c43b3b,0xb67c3a0f,0x381db9ed,0x3be22fd6,0xbaddb95f,0xb179bbf1,
0x3bf634a5,0x33033bb6,0xae46bba8,0x3bce3444,0xb913378b,0xbb77ba0f,0x3a2f3b0e,0xb5c2393a,0xae46bba8,0x3a8aafd6,0xbbf6b4a5,0xb89bbbf1,
0x3a2f3b0e,0x26483b25,0x3913b78b,0x3bff3732,0xbb88b3c6,0xb732bbce,0x35643bc3,0xbb25b303,0x2a48ba6d,0x3bb6367c,0xbbfeb8c4,0xb444bb50,
0x3b3b3add,0x2cb53a8a,0x36d7b81d,0x3bfa389b,0xb9ed30b2,0xbbf1b9cb,0x395f3bea,0xafd63984,0x3aa7323e,0x393a3be2,0xb872bbd9,0x3a0f3179,
0x38723bd9,0xb8ec2648,0x3aa7323e,0x3a4f3bff,0xbaa7b23e,0xbb25bbce,0x38723bd9,0xb7323303,0xb872bbd9,0x3444b67c,0xbaa7b23e,0xbbb6bb50,
0xb95fb0b2,0xba8abbf1,0x39ed3bea,0xb89bafd6,0xbb88bbc3,0x2648b732,0xb56433c6,0xbbffbb25,0xaa48b8c4,0x3ac237e3,0xbbfeba6d,0xb848baf6,
0x3b3b381d,0x3b503bfa,0xb6d7badd,0x367cacb5,0x378b2e46,0x3b773bfa,0xbb0ebbf6,0x35c22cb5,0x3ba83a2f,0x389b3a4f,0xb4a5b913,0x3a8a38ec,
0x3b0e3bf6,0x26483505,0x378b2e46,0x3bff3b99,0x34a53913,0xb848b444,0x3ba83a2f,0x3ac23bb6,0xb3c6aa48,0xbbf1bbff,0x3bc33bfe,0xafd6a648,
0xb8c4b6d7,0xbb99bbce,0x3a6d3b3b,0xb505b303,0xbaddb9ed,0xbaf6bb50,0x381d395f,0xb7e3b67c,0xbbeabb88,0xba0fba8a,0x30b23564,0xb93ab89b,
0x3c003c00,0xba4fb9cb,0,0xb8ecb984,0x3c003c00,0xbb25bac2,0,0xb732b848,0x3c003c00,0xbbb6bb77,0,0xb444b5c2,
0x3c003c00,0xbbfabbe2,0,0xacb5b179,0x33c62a48,0x367c393a,0x3bc33bfe,0xbb50ba0f,0x38c436d7,0xb1792fd6,0x3a6d3b3b,0xbbe2bbf1,
0x3add39ed,0xb984b732,0x381d395f,0xb9cbbb25,0x3bea3b88,0xbbcebaf6,0x30b23564,0xb303b7e3,0xbb0ebbf6,0x3be23a4f,0x378b2e46,0x317938ec,
0xb4a5b913,0x39843b99,0x3ba83a2f,0xb9cbb505,0x378b2e46,0xb3033444,0x3b0e3bf6,0xbbcebbb6,0x3ba83a2f,0xbb77b93a,0x34a53913,0xb5c2ba0f,
0xb95fb0b2,0x2cb5b89b,0xb9edbbea,0x3bfa3a8a,0xbb88bbc3,0x3bf13984,0x3564b3c6,0x2fd639cb,0xaa48b8c4,0x35053ac2,0x3bfe3a6d,0xbb99b848,
0x3b3b381d,0xbaf6b5c2,0x36d73add,0xb7e3bb77,0x38723bd9,0xbb99bac2,0xbaa7b23e,0x3505b848,0xbaa7b23e,0x37e3b5c2,0xb872bbd9,0x3af63b77,
0xb872bbd9,0x3a0f3be2,0x3aa7323e,0xb93a3179,0x3aa7323e,0xba4fa648,0x38723bd9,0xb8ecbbff,0x3b8833c6,0xb84837e3,0x35643bc3,0xbac2baf6,
0xaa483a6d,0xb67cbbfa,0xbbfeb8c4,0x3b502cb5,0xbb3bbadd,0x3be238ec,0x36d7b81d,0xb1793a4f,0x39edb0b2,0xb9843505,0x395f3bea,0xb9cbbb99,
0xae46bba8,0x39843b25,0x3bf634a5,0xb9cb3732,0x3a2f3b0e,0xbbceb7e3,0xb913378b,0x3303baf6,0xbbf6b4a5,0x3b77acb5,0xae46bba8,0x35c23bfa,
0x3913b78b,0xb89b38ec,0x3a2f3b0e,0xba8aba4f,0xbbeab564,0x3af6b67c,0x30b2bb88,0x37e33b50,0x3bc3aa48,0xba0f389b,0x33c63bfe,0xb93aba8a,
0xba6d36d7,0x38ecb9cb,0xb8c4bb3b,0x3a4f3984,0x381db9ed,0xb7323ac2,0x3add395f,0xbb25b848,0xb61f3b64,0xb444bb77,0xbb64b61f,0x3bb6b5c2,
0x361fbb64,0x2cb53be2,0x3b64361f,0xbbfa3179,0xb61f3b64,0x2fd6bbff,0xbb64b61f,0x3bf12648,0x361fbb64,0xb5053bce,0x3b64361f,0xbb99b303,
0x3a6d36d7,0xbbff3505,0xb8c43b3b,0xa648bb99,0xb81db9ed,0x3ac23444,0x3addb95f,0xb8483bb6,0x30b23b88,0xb67cba0f,0xbbea3564,0x3b50b93a,
0x33c6bbfe,0xb1793bf1,0x3bc32a48,0xbbe22fd6,0x3a2fbb0e,0xb3033bb6,0x3913378b,0xbbce3444,0xbbf634a5,0x3b77ba0f,0x2e46bba8,0x35c2393a,
0x3913378b,0xba8aafd6,0xba2f3b0e,0x389bbbf1,0x2e46bba8,0xa6483b25,0x3bf6b4a5,0xbbff3732,0xb6d7b81d,0x3b25b303,0x3b3bbadd,0xb7323bce,
0xb95f3bea,0x3444bb50,0xb9edb0b2,0x3bb6b67c,0x3b88b3c6,0xbbfa389b,0xb5643bc3,0x2cb5ba8a,0xaa48ba6d,0x2fd63984,0x3bfeb8c4,0xbbf139cb,
0xbbd93aa7,0x393abbe2,0xb23eb872,0x3a0fb179,0x323e3872,0xb8eca648,0xbbd93aa7,0x3a4fbbff,0x3bd9baa7,0xbb253bce,0x323e3872,0xb732b303,
0xb23eb872,0x3444367c,0x3bd9baa7,0xbbb63b50,0xaa4838c4,0xb89b2fd6,0xbbfe3a6d,0x3a8abbf1,0x3b3bb81d,0xbbff3b25,0xb6d73add,0xa648b732,
0x39edbbea,0xb8483af6,0x395fb0b2,0xbac237e3,0xb564b3c6,0x367c2cb5,0x3b88bbc3,0xbb503bfa,0x3ba8ba2f,0xbb773bfa,0xb4a53913,0xb5c22cb5,
0x3b0ebbf6,0xb89b3a4f,0x378bae46,0xba8a38ec,0x34a5b913,0xa6483505,0x3ba8ba2f,0xbbff3b99,0xb78b2e46,0x3848b444,0x3b0ebbf6,0xbac23bb6,
0x381db95f,0x2fd6a648,0x3addb9ed,0xbbf13bff,0x30b2b564,0x3505b303,0x3beabb88,0xbb993bce,0xb3c62a48,0x37e3b67c,0x3bc3bbfe,0xbaf63b50,
0xb8c436d7,0x393ab89b,0x3a6dbb3b,0xba0f3a8a,0xb9a839a8,0x3bf1bbff,0x39a8b9a8,0xafd62648,0xb9a839a8,0x3b99bbce,0x39a8b9a8,0xb5053303,
0xb9a839a8,0x3af6bb50,0x39a8b9a8,0xb7e3367c,0xb9a839a8,0x3a0fba8a,0x39a8b9a8,0xb93a389b,0xbadd39ed,0x35c2acb5,0xb81d395f,0x3b77bbfa,
0xbbea3b88,0x3a8ab8ec,0xb0b23564,0x389bba4f,0xbbc33bfe,0x3bffbb99,0x33c6aa48,0x2648b505,0xba6d3b3b,0x3ac2bbb6,0x38c4b6d7,0xb8483444,
0x34a5b913,0xba8a3bf1,0xbba83a2f,0x389bafd6,0xb78b2e46,0x26483732,0xbb0e3bf6,0x3bffbb25,0xbba83a2f,0x3ac2b7e3,0xb4a53913,0x3848baf6,
0xbb0e3bf6,0x3b50bbfa,0x378bae46,0xb67cacb5,0x3bfeba6d,0xba0f3179,0x2a48b8c4,0xb93a3be2,0x36d7badd,0xba4f3bff,0xbb3b381d,0x38ec2648,
0xb95f30b2,0x37323303,0xb9ed3bea,0x3b25bbce,0xbb883bc3,0x3bb6bb50,0x356433c6,0xb444b67c,0x323e3872,0x3732bbce,0x3bd9baa7,0xbb253303,
0x3bd9baa7,0xbbb6367c,0xb23eb872,0xb4443b50,0xb23eb872,0xacb53a8a,0xbbd93aa7,0x3bfab89b,0xbbd93aa7,0x3bf1b9cb,0x323e3872,0xafd6b984,
0xbb3b3add,0x3bceb444,0x36d7381d,0x3303bbb6,0x39ed30b2,0xb5c2b93a,0x395fbbea,0xbb773a0f,0x3564bbc3,0xb89b3bf1,0xbb8833c6,0x3a8a2fd6,
0xbbfe38c4,0x3bffb732,0x2a483a6d,0x2648bb25,0xb913b78b,0x26483b99,0xba2f3b0e,0x3bffb505,0xae463ba8,0x3848bbb6,0x3bf6b4a5,0xbac2b444,
0x3a2fbb0e,0xbb50393a,0xb913b78b,0x367c3a0f,0xbbf634a5,0x3be2afd6,0xae463ba8,0x3179bbf1,0x38c4bb3b,0xbbb635c2,0xba6db6d7,0x34443b77,
0xbadd395f,0x3bfab179,0x381d39ed,0xacb5bbe2,0x3beab564,0xbbf1a648,0xb0b2bb88,0xafd63bff,0xbbc3aa48,0x3b993303,0xb3c63bfe,0x3505bbce,
0x3b64361f,0xb7e3bb50,0x361fbb64,0xbaf6367c,0xbb64b61f,0x393a3a8a,0xb61f3b64,0x3a0fb89b,0x3b64361f,0xba4fb984,0x361fbb64,0xb8ec39cb,
0xbb64b61f,0x3b253848,0xb61f3b64,0x3732bac2,0xb0b23b88,0x39cbb732,0x3bea3564,0xb984bb25,0xb3c6bbfe,0xb3033af6,0xbbc32a48,0x3bce37e3,
0x38c43b3b,0xb5c2bbfa,0x3a6db6d7,0xbb772cb5,0xbaddb95f,0x3a8a3a4f,0xb81d39ed,0x389bb8ec,0xbbf6b4a5,0x3ac23af6,0x2e463ba8,0x3848b7e3,
0x3913b78b,0xbb50acb5,0xba2fbb0e,0x367c3bfa,0x2e463ba8,0x3179ba4f,0x3bf634a5,0xbbe2b8ec,0xba2fbb0e,0x39cb3b99,0xb913378b,0x3984b505,
0xb564bbc3,0xb5053848,0xbb88b3c6,0x3b993ac2,0x3bfe38c4,0xbaf6bb77,0x2a48ba6d,0xb7e335c2,0xb6d7381d,0x393ab179,0x3b3b3add,0xba0fbbe2,
0xb95fbbea,0x38ec3bff,0xb9ed30b2,0x3a4f2648,0x3aa7323e,0xbbfaba8a,0xb872bbd9,0xacb5389b,0x38723bd9,0xafd6b9cb,0x3aa7323e,0xbbf1b984,
0xbaa7b23e,0x3b993848,0x38723bd9,0xb505bac2,0xb872bbd9,0x37e33b77,0xbaa7b23e,0x3af635c2,0x39ed3bea,0xb179b8ec,0x395f30b2,0xbbe2ba4f,
0xb56433c6,0x39cb3505,0x3b883bc3,0xb984bb99,0xbbfeba6d,0x3bce3bb6,0x2a4838c4,0x3303b444,0xb6d7badd,0x35c23a0f,0xbb3bb81d,0x3b77393a,
0xb78bae46,0x3b503a0f,0x3b0e3bf6,0xb67cb93a,0xbba8ba2f,0x3be23bf1,0x34a53913,0x3179afd6,0xbb0ebbf6,0x39cb3b25,0xb78bae46,0x39843732,
0xb4a5b913,0x330337e3,0xbba8ba2f,0x3bce3af6,0xbbc3bbfe,0x38ec3984,0xb3c6aa48,0x3a4f39cb,0xba6dbb3b,0x37323848,0xb8c4b6d7,0x3b253ac2,
0xb81db95f,0x344435c2,0xbaddb9ed,0x3bb63b77,0xb0b2b564,0x2cb53179,0xbbeabb88,0x3bfa3be2,0x3c003c00,0x3a4f39cb,0,0x38ec3984,
0x3c003c00,0x3b253ac2,0,0x37323848,0x3c003c00,0x3bb63b77,0,0x344435c2,0x3c003c00,0x3bfa3be2,0,0x2cb53179,
0x33c62a48,0xb67cb93a,0x3bc33bfe,0x3b503a0f,0x38c436d7,0x3179afd6,0x3a6d3b3b,0x3be23bf1,0x3add39ed,0x39843732,0x381d395f,0x39cb3b25,
0x3bea3b88,0x3bce3af6,0x30b23564,0x330337e3,0xbb0ebbf6,0xbbe2ba4f,0x378b2e46,0xb179b8ec,0xb4a5b913,0xb984bb99,0x3ba83a2f,0x39cb3505,
0x378b2e46,0x3303b444,0x3b0e3bf6,0x3bce3bb6,0x3ba83a2f,0x3b77393a,0x34a53913,0x35c23a0f,0xb95fb0b2,0xacb5389b,0xb9edbbea,0xbbfaba8a,
0xbb88bbc3,0xbbf1b984,0x3564b3c6,0xafd6b9cb,0xaa48b8c4,0xb505bac2,0x3bfe3a6d,0x3b993848,0x3b3b381d,0x3af635c2,0x36d73add,0x37e33b77,
0x38723bd9,0x3b993ac2,0xbaa7b23e,0xb5053848,0xbaa7b23e,0xb7e335c2,0xb872bbd9,0xbaf6bb77,0xb872bbd9,0xba0fbbe2,0x3aa7323e,0x393ab179,
0x3aa7323e,0x3a4f2648,0x38723bd9,0x38ec3bff,0x3b8833c6,0x3848b7e3,0x35643bc3,0x3ac23af6,0xaa483a6d,0x367c3bfa,0xbbfeb8c4,0xbb50acb5,
0xbb3bbadd,0xbbe2b8ec,0x36d7b81d,0x3179ba4f,0x39edb0b2,0x3984b505,0x395f3bea,0x39cb3b99,0xae46bba8,0xb984bb25,0x3bf634a5,0x39cbb732,
0x3a2f3b0e,0x3bce37e3,0xb913378b,0xb3033af6,0xbbf6b4a5,0xbb772cb5,0xae46bba8,0xb5c2bbfa,0x3913b78b,0x389bb8ec,0x3a2f3b0e,0x3a8a3a4f,
0xbbeab564,0xbaf6367c,0x30b2bb88,0xb7e3bb50,0x3bc3aa48,0x3a0fb89b,0x33c63bfe,0x393a3a8a,0xba6d36d7,0xb8ec39cb,0xb8c4bb3b,0xba4fb984,
0x381db9ed,0x3732bac2,0x3add395f,0x3b253848,0xb61f3b64,0x34443b77,0xbb64b61f,0xbbb635c2,0x361fbb64,0xacb5bbe2,0x3b64361f,0x3bfab179,
0xb61f3b64,0xafd63bff,0xbb64b61f,0xbbf1a648,0x361fbb64,0x3505bbce,0x3b64361f,0x3b993303,0x3a6d36d7,0x3bffb505,0xb8c43b3b,0x26483b99,
0xb81db9ed,0xbac2b444,0x3addb95f,0x3848bbb6,0x30b23b88,0x367c3a0f,0xbbea3564,0xbb50393a,0x33c6bbfe,0x3179bbf1,0x3bc32a48,0x3be2afd6,
0x3a2fbb0e,0x3303bbb6,0x3913378b,0x3bceb444,0xbbf634a5,0xbb773a0f,0x2e46bba8,0xb5c2b93a,0x3913378b,0x3a8a2fd6,0xba2f3b0e,0xb89b3bf1,
0x2e46bba8,0x2648bb25,0x3bf6b4a5,0x3bffb732,0xb6d7b81d,0xbb253303,0x3b3bbadd,0x3732bbce,0xb95f3bea,0xb4443b50,0xb9edb0b2,0xbbb6367c,
0x3b88b3c6,0x3bfab89b,0xb5643bc3,0xacb53a8a,0xaa48ba6d,0xafd6b984,0x3bfeb8c4,0x3bf1b9cb,0xbbd93aa7,0xb93a3be2,0xb23eb872,0xba0f3179,
0x323e3872,0x38ec2648,0xbbd93aa7,0xba4f3bff,0x3bd9baa7,0x3b25bbce,0x323e3872,0x37323303,0xb23eb872,0xb444b67c,0x3bd9baa7,0x3bb6bb50,
0xaa4838c4,0x389bafd6,0xbbfe3a6d,0xba8a3bf1,0x3b3bb81d,0x3bffbb25,0xb6d73add,0x26483732,0x39edbbea,0x3848baf6,0x395fb0b2,0x3ac2b7e3,
0xb564b3c6,0xb67cacb5,0x3b88bbc3,0x3b50bbfa,0x3ba8ba2f,0x3b77bbfa,0xb4a53913,0x35c2acb5,0x3b0ebbf6,0x389bba4f,0x378bae46,0x3a8ab8ec,
0x34a5b913,0x2648b505,0x3ba8ba2f,0x3bffbb99,0xb78b2e46,0xb8483444,0x3b0ebbf6,0x3ac2bbb6,0x381db95f,0xafd62648,0x3addb9ed,0x3bf1bbff,
0x30b2b564,0xb5053303,0x3beabb88,0x3b99bbce,0xb3c62a48,0xb7e3367c,0x3bc3bbfe,0x3af6bb50,0xb8c436d7,0xb93a389b,0x3a6dbb3b,0x3a0fba8a,
0xb9a839a8,0xbbf13bff,0x39a8b9a8,0x2fd6a648,0xb9a839a8,0xbb993bce,0x39a8b9a8,0x3505b303,0xb9a839a8,0xbaf63b50,0x39a8b9a8,0x37e3b67c,
0xb9a839a8,0xba0f3a8a,0x39a8b9a8,0x393ab89b,0xbadd39ed,0xb5c22cb5,0xb81d395f,0xbb773bfa,0xbbea3b88,0xba8a38ec,0xb0b23564,0xb89b3a4f,
0xbbc33bfe,0xbbff3b99,0x33c6aa48,0xa6483505,0xba6d3b3b,0xbac23bb6,0x38c4b6d7,0x3848b444,0x34a5b913,0x3a8abbf1,0xbba83a2f,0xb89b2fd6,
0xb78b2e46,0xa648b732,0xbb0e3bf6,0xbbff3b25,0xbba83a2f,0xbac237e3,0xb4a53913,0xb8483af6,0xbb0e3bf6,0xbb503bfa,0x378bae46,0x367c2cb5,
0x3bfeba6d,0x3a0fb179,0x2a48b8c4,0x393abbe2,0x36d7badd,0x3a4fbbff,0xbb3b381d,0xb8eca648,0xb95f30b2,0xb732b303,0xb9ed3bea,0xbb253bce,
0xbb883bc3,0xbbb63b50,0x356433c6,0x3444367c,0x323e3872,0xb7323bce,0x3bd9baa7,0x3b25b303,0x3bd9baa7,0x3bb6b67c,0xb23eb872,0x3444bb50,
0xb23eb872,0x2cb5ba8a,0xbbd93aa7,0xbbfa389b,0xbbd93aa7,0xbbf139cb,0x323e3872,0x2fd63984,0xbb3b3add,0xbbce3444,0x36d7381d,0xb3033bb6,
0x39ed30b2,0x35c2393a,0x395fbbea,0x3b77ba0f,0x3564bbc3,0x389bbbf1,0xbb8833c6,0xba8aafd6,0xbbfe38c4,0xbbff3732,0x2a483a6d,0xa6483b25,
0xb913b78b,0xa648bb99,0xba2f3b0e,0xbbff3505,0xae463ba8,0xb8483bb6,0x3bf6b4a5,0x3ac23444,0x3a2fbb0e,0x3b50b93a,0xb913b78b,0xb67cba0f,
0xbbf634a5,0xbbe22fd6,0xae463ba8,0xb1793bf1,0x38c4bb3b,0x3bb6b5c2,0xba6db6d7,0xb444bb77,0xbadd395f,0xbbfa3179,0x381d39ed,0x2cb53be2,
0x3beab564,0x3bf12648,0xb0b2bb88,0x2fd6bbff,0xbbc3aa48,0xbb99b303,0xb3c63bfe,0xb5053bce,0x3b64361f,0x37e33b50,0x361fbb64,0x3af6b67c,
0xbb64b61f,0xb93aba8a,0xb61f3b64,0xba0f389b,0x3b64361f,0x3a4f3984,0x361fbb64,0x38ecb9cb,0xbb64b61f,0xbb25b848,0xb61f3b64,0xb7323ac2,
0xb0b23b88,0xb9cb3732,0x3bea3564,0x39843b25,0xb3c6bbfe,0x3303baf6,0xbbc32a48,0xbbceb7e3,0x38c43b3b,0x35c23bfa,0x3a6db6d7,0x3b77acb5,
0xbaddb95f,0xba8aba4f,0xb81d39ed,0xb89b38ec,0xbbf6b4a5,0xbac2baf6,0x2e463ba8,0xb84837e3,0x3913b78b,0x3b502cb5,0xba2fbb0e,0xb67cbbfa,
0x2e463ba8,0xb1793a4f,0x3bf634a5,0x3be238ec,0xba2fbb0e,0xb9cbbb99,0xb913378b,0xb9843505,0xb564bbc3,0x3505b848,0xbb88b3c6,0xbb99bac2,
0x3bfe38c4,0x3af63b77,0x2a48ba6d,0x37e3b5c2,0xb6d7381d,0xb93a3179,0x3b3b3add,0x3a0f3be2,0xb95fbbea,0xb8ecbbff,0xb9ed30b2,0xba4fa648,
0x3aa7323e,0x3bfa3a8a,0xb872bbd9,0x2cb5b89b,0x38723bd9,0x2fd639cb,0x3aa7323e,0x3bf13984,0xbaa7b23e,0xbb99b848,0x38723bd9,0x35053ac2,
0xb872bbd9,0xb7e3bb77,0xbaa7b23e,0xbaf6b5c2,0x39ed3bea,0x317938ec,0x395f30b2,0x3be23a4f,0xb56433c6,0xb9cbb505,0x3b883bc3,0x39843b99,
0xbbfeba6d,0xbbcebbb6,0x2a4838c4,0xb3033444,0xb6d7badd,0xb5c2ba0f,0xbb3bb81d,0xbb77b93a,0xb78bae46,0xbb50ba0f,0x3b0e3bf6,0x367c393a,
0xbba8ba2f,0xbbe2bbf1,0x34a53913,0xb1792fd6,0xbb0ebbf6,0xb9cbbb25,0xb78bae46,0xb984b732,0xb4a5b913,0xb303b7e3,0xbba8ba2f,0xbbcebaf6,
0xbbc3bbfe,0xb8ecb984,0xb3c6aa48,0xba4fb9cb,0xba6dbb3b,0xb732b848,0xb8c4b6d7,0xbb25bac2,0xb81db95f,0xb444b5c2,0xbaddb9ed,0xbbb6bb77,
0xb0b2b564,0xacb5b179,0xbbeabb88,0xbbfabbe2,0x3c003c00,0x96480000,0x3c003c00,0xa311a248,0x3c003c00,0x9cb69a48,0x3c003c00,0xa452a3db,
0x3c003c00,0x9fdb9e48,0x3c003c00,0xa51ba4b6,0x3c003c00,0xa17fa0b6,0x3bff3c00,0xa5e4a57f,0x3c003c00,0x9fdb0000,0x3bfb3bfc,0xac6aabd9,
0x3bff3c00,0xa5e4a3db,0x3bf93bfa,0xad65ace7,0x3bfe3bff,0xa8e8a7da,0x3bf63bf7,0xae5fade2,0x3bfd3bfe,0xaadea9e3,0x3bf23bf4,0xaf59aedc,
0x3c003c00,0xa3110000,0x3bf03bf4,0xafefaf0e,0x3bfe3bff,0xa94da711,0x3be83bed,0xb0d7b067,0x3bfb3bfd,0xac6aab11,0x3bdf3be4,0xb1b6b147,
0x3bf63bf9,0xae2dad4c,0x3bd43bda,0xb294b226,0x3c003c00,0xa51b0000,0x3bdf3be6,0xb1b6b115,0x3bfc3bfe,0xaba7a91b,0x3bcf3bd7,0xb2f7b257,
0x3bf63bf9,0xae5fad1a,0x3bbc3bc6,0xb41ab396,0x3bec3bf1,0xb074afa4,0x3ba53bb1,0xb4b7b469,0x3bff3c00,0xa6ad0000,0x3bc83bd4,0xb371b2a1,
0x3bfa3bfd,0xad00aaac,0x3bac3bbb,0xb487b420,0x3bef3bf5,0xb029aeaa,0x3b8b3b9d,0xb552b4ed,0x3bde3be7,0xb1cfb0fd,0x3b653b79,0xb61ab5b6,
0x3bff3c00,0xa81f0000,0x3bab3bbc,0xb493b414,0x3bf63bfc,0xae2dac1f,0x3b813b97,0xb58db511,0x3be53bef,0xb122b01d,0x3b4f3b69,0xb682b608,
0x3bcc3bda,0xb328b226,0x3b163b33,0xb76fb6f9,0x3bfe3c00,0xa8e80000,0x3b873ba0,0xb56ab4d5,0x3bf23bfa,0xaf59ace7,0x3b4c3b6b,0xb68db5fd,
0x3bda3be8,0xb219b0e4,0x3b073b2b,0xb7a6b71b,0x3bb73bca,0xb43eb34c,0x3ab63ae0,0xb85ab817,0x3bfe3c00,0xa9b10000,0x3b5e3b80,0xb63cb593,
0x3bee3bf8,0xb042adb0,0x3b103b39,0xb785b6e3,0x3bce3be0,0xb30fb1aa,0x3ab33ae3,0xb85fb812,0x3b9e3bb7,0xb4e7b438,0x3a493a7f,0xb8f3b8ab,
0x3bfd3c00,0xaa7a0000,0x3b2f3b5a,0xb70ab64e,0x3be83bf6,0xb0d7ae78,0x3acb3aff,0xb83ab7c2,0x3bbf3bd6,0xb402b26f,0x3a543a92,0xb8e5b891,
0x3b813ba2,0xb58db4c9,0x39cd3a13,0xb982b935,0x3bfd3c00,0xab430000,0x3afb3b30,0xb7d2b705,0x3be23bf3,0xb16caf40,0x3a7e3abf,0xb8adb84d,
0x3bae3bcb,0xb47bb334,0x39eb3a37,0xb962b909,0x3b603b8a,0xb631b558,0x3946399b,0xba04b9b5,0x3bfc3c00,0xac060000,0x3ac13b02,0xb84ab7b7,
0x3bdc3bf0,0xb201b004,0x3a293a78,0xb91bb8b5,0x3b9c3bc0,0xb4f3b3f7,0x397939d4,0xb9d6b97b,0x3b3d3b70,0xb6d2b5e5,0x38b23918,0xba7aba2b,
0x3bfb3c00,0xac6a0000,0x3a813ad0,0xb8a8b832,0x3bd43bed,0xb294b067,0x39cd3a2b,0xb982b918,0x3b873bb2,0xb56ab45d,0x38fd3969,0xba41b9e5,
0x3b163b53,0xb76fb670,0x3815388c,0xbae1ba95,0x3bfa3c00,0xacce0000,0x3a3d3a99,0xb902b887,0x3bcc3be9,0xb328b0cb,0x396b39d8,0xb9e3b976,
0x3b713ba4,0xb5dfb4bd,0x387a38f6,0xbaa2ba47,0x3aeb3b33,0xb805b6f9,0x36dd37ee,0xbb3abaf3,0x3bf93c00,0xad330000,0x39f43a5e,0xb958b8d8,
0x3bc33be5,0xb3bab12e,0x39023980,0xba3db9d0,0x3b593b95,0xb654b51d,0x37dd387c,0xbaf7baa0,0x3abd3b11,0xb850b780,0x358136b5,0xbb83bb43,
0x3bf83c00,0xad970000,0x39a63a1f,0xb9aab927,0x3bba3be1,0xb426b191,0x38943922,0xba90ba23,0x3b3f3b84,0xb6c6b57c,0x36bb37f9,0xbb42baf0,
0x3a8c3aed,0xb899b802,0x341a3570,0xbbbcbb86,0x3bf73c00,0xadfb0000,0x395439dc,0xb9f8b972,0x3bb03bdc,0xb46fb1f4,0x382038bf,0xbadbba71,
0x3b243b72,0xb737b5da,0x358d36ee,0xbb81bb36,0x3a583ac6,0xb8e0b842,0x31533420,0xbbe3bbbb,0x3bf63c00,0xae5f0000,0x38fd3996,0xba41b9ba,
0x3ba53bd7,0xb4b7b257,0x374e3858,0xbb1ebab8,0x3b073b5f,0xb7a6b637,0x345735da,0xbbb3bb72,0x3a213a9c,0xb924b881,0x2cce3191,0xbbfabbe1,
0x3bf53c00,0xaec30000,0x38a3394d,0xba85b9fe,0x3b9a3bd2,0xb4ffb2b9,0x365437d8,0xbb59baf9,0x3ae83b4b,0xb80ab693,0x323234bd,0xbbd9bba4,
0x39e73a71,0xb966b8bf,0xa4522db0,0xbc00bbf8,0x3bf33c00,0xaf270000,0x38453900,0xbac4ba3f,0x3b8e3bcd,0xb546b31b,0x355236f9,0xbb8bbb33,
0x3ac73b36,0xb840b6ee,0x2f593334,0xbbf2bbcb,0x39aa3a43,0xb9a6b8fb,0xaef51a48,0xbbf4bc00,0x3bf23c00,0xaf8b0000,0x37c838b0,0xbafeba7c,
0x3b813bc7,0xb58db37d,0x344b3614,0xbbb5bb67,0x3aa53b20,0xb874b748,0x288430e4,0xbbffbbe8,0x396b3a13,0xb9e3b935,0xb263ad4c,0xbbd7bbf9,
0x3bf03c00,0xafef0000,0x36ff385d,0xbb32bab5,0x3b733bc1,0xb5d4b3df,0x327c3529,0xbbd6bb93,0x3a813b08,0xb8a8b7a1,0xa9b12d1a,0xbbfebbf9,
0x392939e1,0xba1db96d,0xb49fb160,0xbba9bbe3,0x3bef3c00,0xb0290000,0x36313807,0xbb60bae9,0x3b653bbb,0xb61ab420,0x305b3438,0xbbedbbb7,
0x3a5c3af0,0xb8dbb7f9,0xafef1e48,0xbbf0bc00,0x38e539ad,0xba54b9a4,0xb602b408,0xbb6abbbe,0x3bed3c00,0xb05b0000,0x355e375e,0xbb89bb1a,
0x3b573bb4,0xb65fb451,0x2c6a3288,0xbbfbbbd5,0x3a353ad6,0xb90cb828,0xb27cac51,0xbbd6bbfb,0x389e3976,0xba89b9d8,0xb759b558,0xbb1bbb8a,
0x3beb3c00,0xb08d0000,0x348736aa,0xbbacbb46,0x3b473bad,0xb6a4b481,0x16483099,0xbc00bbeb,0x3a0d3abc,0xb93cb852,0xb47bb080,0xbbaebbec,
0x3855393e,0xbababa0b,0xb850b69e,0xbabdbb49,0x3be93c00,0xb0be0000,0x335935f1,0xbbc9bb6e,0x3b373ba6,0xb6e8b4b1,0xac382d4c,0xbbfcbbf9,
0x39e33aa0,0xb96bb87c,0xb5b1b2d2,0xbb7abbd1,0x380a3905,0xbae8ba3b,0xb8eab7d8,0xba50baf9,0x3be73c00,0xb0f00000,0x319e3534,0xbbe0bb91,
0x3b273b9e,0xb72cb4e1,0xb042257f,0xbbeebc00,0x39b83a83,0xb999b8a6,0xb6ddb48d,0xbb3abbab,0x377a38c9,0xbb13ba69,0xb979b881,0xb9d6ba9c,
0x3be53c00,0xb1220000,0x2fbd3475,0xbbf1bbaf,0x3b163b97,0xb76fb511,0xb263a91b,0xbbd7bbfe,0x398b3a65,0xb9c5b8ce,0xb7feb5ab,0xbaeebb7b,
0x36dd388c,0xbb3aba95,0xb9fcb90e,0xb94fba33,0x3be33c00,0xb1530000,0x2c383365,0xbbfcbbc9,0x3b043b8f,0xb7b2b540,0xb43eae78,0xbbb7bbf6,
0x395d3a47,0xb9f0b8f6,0xb889b6c1,0xba97bb41,0x363c384d,0xbb5ebabf,0xba73b992,0xb8bcb9be,0x3be13c00,0xb1850000,0x217f31db,0xbc00bbdd,
0x3af13b86,0xb7f3b570,0xb546b12e,0xbb8ebbe5,0x392e3a27,0xba19b91d,0xb90cb7cd,0xba35bafc,0x3599380d,0xbb7fbae6,0xbadbba0b,0xb820b93e,
0x3bdf3c00,0xb1b60000,0xa9b1304e,0xbbfebbed,0x3ade3b7d,0xb81ab59f,0xb648b31b,0xbb5cbbcd,0x38fd3a07,0xba41b943,0xb986b867,0xb9c9baae,
0x34f33796,0xbb9cbb0b,0xbb35ba78,0xb6f4b8b5,0x3bdd3c00,0xb1e80000,0xae5f2d7e,0xbbf6bbf8,0x3acb3b74,0xb83ab5ce,0xb742b481,0xbb21bbad,
0x38cc39e5,0xba67b969,0xb9f8b8e2,0xb954ba56,0x344b3710,0xbbb5bb2e,0xbb7fbad9,0xb599b822,0x3bda3c00,0xb2190000,0xb0f028b6,0xbbe7bbff,
0x3ab63b6b,0xb85ab5fd,0xb81ab570,0xbadebb86,0x389939c3,0xba8cb98d,0xba60b956,0xb8d6b9f6,0x33403687,0xbbcbbb4e,0xbbb8bb2e,0xb432b710,
0x3bff3bff,0xa6ada648,0x3bfe3bff,0xa8e8a8b6,0x3bff3bff,0xa776a711,0x3bfe3bfe,0xa94da91b,0x3bff3bff,0xa81fa7da,0x3bfe3bfe,0xa9b1a97f,
0x3bff3bff,0xa884a852,0x3bfe3bfe,0xaa16a9e3,0x3bef3bf1,0xb029afd6,0x3bda3bdd,0xb219b1db,0x3bea3bed,0xb0a6b067,0x3bd43bd7,0xb294b257,
0x3be53be8,0xb122b0e4,0x3bce3bd1,0xb30fb2d2,0x3be03be3,0xb19eb160,0x3bc63bca,0xb389b34c,0x3bc83bce,0xb371b303,0x3b873b91,0xb56ab534,
0x3bba3bc1,0xb426b3df,0x3b733b7d,0xb5d4b59f,0x3bab3bb2,0xb493b45d,0x3b5e3b69,0xb63cb608,0x3b9a3ba2,0xb4ffb4c9,0x3b473b53,0xb6a4b670,
0x3b8b3b99,0xb552b505,0x3b073b1a,0xb7a6b75e,0x3b6f3b7d,0xb5ebb59f,0x3ade3af3,0xb81ab7ee,0x3b4f3b5f,0xb682b637,0x3ab33ac9,0xb85fb83d,
0x3b2c3b3e,0xb715b6cc,0x3a853a9c,0xb8a3b881,0x3b3a3b50,0xb6ddb67c,0x3a5c3a7c,0xb8dbb8b0,0x3b0a3b22,0xb79bb73d,0x3a193a3b,0xb92eb905,
0x3ad53af0,0xb82ab7f9,0x39d239f6,0xb97db956,0x3a9b3ab8,0xb884b858,0x398639ad,0xb9c9b9a4,0x3ad53af6,0xb82ab7e3,0x398b39ba,0xb9c5b996,
0x3a8c3ab1,0xb899b862,0x3929395b,0xba1db9f2,0x3a3d3a65,0xb902b8ce,0x38c138f6,0xba6fba47,0x39e73a13,0xb966b935,0x3855388c,0xbababa95,
0x3a5c3a8a,0xb8dbb89b,0x389938d8,0xba8cba5e,0x39f83a2b,0xb954b918,0x38153858,0xbae1bab8,0x398b39c3,0xb9c5b98d,0x371537a1,0xbb2cbb08,
0x39163951,0xba2db9fa,0x35f73687,0xbb6cbb4e,0x39d23a0f,0xb97db93a,0x371537b7,0xbb2cbb02,0x394f3992,0xb9fcb9be,0x35c83670,0xbb76bb53,
0x38c13909,0xba6fba37,0x346f351d,0xbbb0bb95,0x382a3877,0xbad5baa3,0x3219337d,0xbbdabbc7,0x39373984,0xba11b9cb,0x34cf3593,0xbba1bb80,
0x389438e7,0xba90ba52,0x327c3408,0xbbd6bbbe,0x37c8383d,0xbafebac9,0x2e9130e4,0xbbf5bbe8,0x36543710,0xbb59bb2e,0x16482aac,0xbc00bbfd,
0x388e38ec,0xba93ba4f,0x30d732a1,0xbbe8bbd4,0x3790382d,0xbb0dbad3,0x28e82e14,0xbbfebbf7,0x35eb36c1,0xbb6fbb41,0xaccea4b6,0xbbfabc00,
0x34323511,0xbbb8bb97,0xb201b036,0xbbdcbbee,0x37b23848,0xbb04bac2,0x96482bd9,0xbc00bbfc,0x35df36cc,0xbb71bb3e,0xb010ac1f,0xbbefbbfc,
0x33eb34ed,0xbbc0bb9d,0xb402b20d,0xbbbfbbdb,0x2fef31f4,0xbbf0bbdc,0xb5ebb4f9,0xbb6fbb9b,0x36313732,0xbb60bb25,0xb0f0ad7e,0xbbe7bbf8,
0x341a3529,0xbbbcbb93,0xb49fb31b,0xbba9bbcd,0x2fbd320d,0xbbf1bbdb,0xb6afb5ab,0xbb45bb7b,0xa4522aac,0xbc00bbfd,0xb850b7ac,0xbabdbb05,
0x349f35c2,0xbba9bb77,0xb4dbb365,0xbb9fbbc9,0x308d32ea,0xbbebbbd0,0xb715b5fd,0xbb2cbb6b,0x9fdb2c51,0xbc00bbfb,0xb894b812,0xba90bae3,
0xb109ad4c,0xbbe6bbf9,0xb982b90e,0xb9cdba33,0x32013444,0xbbdcbbb6,0xb721b5f1,0xbb2abb6e,0x26ad2edc,0xbbffbbf4,0xb8adb822,0xba7ebad9,
0xb05bab11,0xbbedbbfd,0xb9aab930,0xb9a6ba17,0xb4b7b2ea,0xbba5bbd0,0xba81ba1b,0xb8a8b92b,0x2d653179,0xbbf9bbe2,0xb89eb807,0xba89bae9,
0xadc99a48,0xbbf8bc00,0xb9afb92b,0xb9a1ba1b,0xb432b1aa,0xbbb8bbe0,0xba93ba27,0xb88eb91d,0xb6d2b587,0xbb3dbb82,0xbb45baf3,0xb6afb7ee,
0xa51b2cb5,0xbc00bbfa,0xb990b900,0xb9c0ba3f,0xb294af40,0xbbd4bbf3,0xba89ba13,0xb89eb935,0xb625b4bd,0xbb63bba4,0xbb47baf0,0xb6a4b7f9,
0xb865b780,0xbab0bb11,0xbbc5bb8f,0xb3a2b540,0xafefa648,0xbbf0bbff,0xba60b9dc,0xb8d6b972,0xb517b31b,0xbb96bbcd,0xbb35bad3,0xb6f4b82d,
0xb7feb693,0xbaeebb4b,0xbbc0bb84,0xb3ebb57c,0xb94ab8ab,0xba00ba7f,0xbbfdbbe9,0xaa7ab0cb,0xb340afd6,0xbbcbbbf1,0xbb0aba99,0xb79bb887,
0xb6d2b540,0xbb3dbb8f,0xbbaebb67,0xb47bb614,0xb8dbb828,0xba5cbad6,0xbbfbbbe0,0xac9cb1aa,0xba15b980,0xb933b9d0,0xbbecbbff,0x30742852,
0xb53ab303,0xbb90bbce,0xbb89bb30,0xb55eb705,0xb83ab6e3,0xbacbbb39,0xbbf2bbca,0xaf8bb34c,0xb9a1b8f6,0xb9afba47,0xbbf5bc00,0x2ec39e48,
0xbac1ba3b,0xb84ab905,0xbb92bbd0,0x352f32ea,0xb6c6b505,0xbb3fbb99,0xbbdcbba0,0xb201b4d5,0xb8fdb838,0xba41bacc,0xbbfebbfb,0x2a16ac83,
0xba50b9b1,0xb8eab99f,0xbbaebbe4,0x347b3147,0xbb4abad9,0xb699b822,0xbaf1bb5d,0x37f33642,0xb820b67c,0xbadbbb50,0xbbffbbe6,0xa884b115,
0xb9afb8f1,0xb9a1ba4b,0xbbd2bbf8,0x32c62db0,0xbae5ba56,0xb80fb8e2,0xbb2abb8c,0x3721354c,0xbbaebb58,0xb47bb659,0xba11baaa,0x3937386d,
0xb8d1b7e3,0xba64baf6,0xbbf2bc00,0x2f8ba248,0xba4db99b,0xb8eeb9b5,0xbb6fbbc1,0x35eb33df,0xbb5cbae3,0xb648b812,0xba6bbafc,0x38c737cd,
0xbbebbbb4,0xb08db451,0xb8f8b9be,0x3a453992,0xb974b89b,0xb9daba8a,0xbbb5bbed,0x344b304e,0xbad5ba33,0xb82ab90e,0xbad8bb58,0x38253659,
0xbbb3bb55,0xb457b665,0xb979ba37,0x39d63909,0xbc00bbed,0x9648b067,0xb764b8a0,0x3b183a87,0xba09b93a,0xb941ba0f,0xbb4abbaf,0x36993475,
0xbb45bab8,0xb6afb858,0xba11babf,0x3937384d,0xbbeabbab,0xb0a6b48d,0xb85ab943,0x3ab63a07,0xbbecbc00,0x30749a48,0xb493b6b5,0x3bab3b43,
0xba8cb9cb,0xb899b984,0xbab3bb46,0x385f36aa,0xbb9cbb28,0xb4f3b726,0xb91fb9fa,0x3a253951,0xbc00bbe4,0xa452b147,0xb631b828,0x3b603ad6,
0xbbb0bbee,0x346f3036,0xae5fb3df,0x3bf63bc1,0xbafeba4f,0xb7c8b8ec,0xb9f4bab5,0x3958385d,0xbbd8bb82,0xb24bb587,0xb80ab90e,0x3ae83a33,
0xbbf3bbfe,0x2f27a97f,0xb2f7b5da,0x3bcf3b72,0xbb4cbbb7,0x368d3438,0x2dc9ac1f,0x3bf83bfc,0xbb5cbac2,0xb648b848,0xb911b9fe,0x3a31394d,
0xbbf9bbc4,0xad33b3ae,0xb5b1b802,0x3b7a3aed,0xbbc5bbf9,0x33a22d1a,0xa94db26f,0x3bfe3bd6,0xbac4bb5d,0x38453642,0x346f2fa4,0x3bb03bf1,
0xbba5bb25,0xb4b7b732,0xb80fb927,0x3ae53a1f,0xbbffbbee,0x2884b036,0xb24bb5b6,0x3bd83b79,0xbb76bbd6,0x35c8326f,0x305ba7da,0x3bed3bff,
0xba19bae0,0x392e3817,0x374234c9,0x3b213ba2,0xbbd9bb77,0xb232b5c2,0xb5ebb832,0x3b6f3ad0,0xbbe8bc00,0x30d7a57f,0xa81fb288,0x3bff3bd5,
0xbb07bb95,0x37a6351d,0x34f33080,0x3b9c3bec,0xb94fba43,0x39fc38fb,0x38ea3780,0x3a503b11,0xbbf8bbb6,0xadc9b444,0xb328b64e,0x3bcc3b5a,
0xbbb7bbf8,0x343e2db0,0x3042a9e3,0x3bee3bfe,0xba7abb36,0x38b236ee,0x379034ed,0x3b0d3b9d,0xb86ab989,0x3aac39c7,0x3a0438fb,0x39463a43,
0xbc00bbe2,0x2311b179,0xac9cb414,0x3bfb3bbc,0xbb6abbd7,0x36023257,0x34b72f40,0x3ba53bf3,0xb9d2babc,0x397d3852,0x38f83775,0x3a453b14,
0xb6ddb8b5,0x3b3a3a78,0x3ae83a0b,0x380a393e,0xbbf2bbfa,0x2f8bacb5,0x2d33af0e,0x3bf93bf4,0xbb04bb9e,0x37b234e1,0x372c3451,0x3b273bb4,
0xb911ba27,0x3a31391d,0x3a0038e2,0x394a3a56,0xb4c3b796,0x3ba33b0b,0x3b8b3ae6,0x3552380d,0x4c004c00,0x26480000,0x4c004c00,0x33113248,
0x4c004c00,0x2cb62a48,0x4c004c00,0x345233db,0x4c004c00,0x2fdb2e48,0x4c004c00,0x351b34b6,0x4c004c00,0x317f30b6,0x4bff4c00,0x35e4357f,
0x4c004c00,0x2fdb0000,0x4bfb4bfc,0x3c6a3bd9,0x4bff4c00,0x35e433db,0x4bf94bfa,0x3d653ce7,0x4bfe4bff,0x38e837da,0x4bf64bf7,0x3e5f3de2,
0x4bfd4bfe,0x3ade39e3,0x4bf24bf4,0x3f593edc,0x4c004c00,0x33110000,0x4bf04bf4,0x3fef3f0e,0x4bfe4bff,0x394d3711,0x4be84bed,0x40d74067,
0x4bfb4bfd,0x3c6a3b11,0x4bdf4be4,0x41b64147,0x4bf64bf9,0x3e2d3d4c,0x4bd44bda,0x42944226,0x4c004c00,0x351b0000,0x4bdf4be6,0x41b64115,
0x4bfc4bfe,0x3ba7391b,0x4bcf4bd7,0x42f74257,0x4bf64bf9,0x3e5f3d1a,0x4bbc4bc6,0x441a4396,0x4bec4bf1,0x40743fa4,0x4ba54bb1,0x44b74469,
0x4bff4c00,0x36ad0000,0x4bc84bd4,0x437142a1,0x4bfa4bfd,0x3d003aac,0x4bac4bbb,0x44874420,0x4bef4bf5,0x40293eaa,0x4b8b4b9d,0x455244ed,
0x4bde4be7,0x41cf40fd,0x4b654b79,0x461a45b6,0x4bff4c00,0x381f0000,0x4bab4bbc,0x44934414,0x4bf64bfc,0x3e2d3c1f,0x4b814b97,0x458d4511,
0x4be54bef,0x4122401d,0x4b4f4b69,0x46824608,0x4bcc4bda,0x43284226,0x4b164b33,0x476f46f9,0x4bfe4c00,0x38e80000,0x4b874ba0,0x456a44d5,
0x4bf24bfa,0x3f593ce7,0x4b4c4b6b,0x468d45fd,0x4bda4be8,0x421940e4,0x4b074b2b,0x47a6471b,0x4bb74bca,0x443e434c,0x4ab64ae0,0x485a4817,
0x4bfe4c00,0x39b10000,0x4b5e4b80,0x463c4593,0x4bee4bf8,0x40423db0,0x4b104b39,0x478546e3,0x4bce4be0,0x430f41aa,0x4ab34ae3,0x485f4812,
0x4b9e4bb7,0x44e74438,0x4a494a7f,0x48f348ab,0x4bfd4c00,0x3a7a0000,0x4b2f4b5a,0x470a464e,0x4be84bf6,0x40d73e78,0x4acb4aff,0x483a47c2,
0x4bbf4bd6,0x4402426f,0x4a544a92,0x48e54891,0x4b814ba2,0x458d44c9,0x49cd4a13,0x49824935,0x4bfd4c00,0x3b430000,0x4afb4b30,0x47d24705,
0x4be24bf3,0x416c3f40,0x4a7e4abf,0x48ad484d,0x4bae4bcb,0x447b4334,0x49eb4a37,0x49624909,0x4b604b8a,0x46314558,0x4946499b,0x4a0449b5,
0x4bfc4c00,0x3c060000,0x4ac14b02,0x484a47b7,0x4bdc4bf0,0x42014004,0x4a294a78,0x491b48b5,0x4b9c4bc0,0x44f343f7,0x497949d4,0x49d6497b,
0x4b3d4b70,0x46d245e5,0x48b24918,0x4a7a4a2b,0x4bfb4c00,0x3c6a0000,0x4a814ad0,0x48a84832,0x4bd44bed,0x42944067,0x49cd4a2b,0x49824918,
0x4b874bb2,0x456a445d,0x48fd4969,0x4a4149e5,0x4b164b53,0x476f4670,0x4815488c,0x4ae14a95,0x4bfa4c00,0x3cce0000,0x4a3d4a99,0x49024887,
0x4bcc4be9,0x432840cb,0x496b49d8,0x49e34976,0x4b714ba4,0x45df44bd,0x487a48f6,0x4aa24a47,0x4aeb4b33,0x480546f9,0x46dd47ee,0x4b3a4af3,
0x4bf94c00,0x3d330000,0x49f44a5e,0x495848d8,0x4bc34be5,0x43ba412e,0x49024980,0x4a3d49d0,0x4b594b95,0x4654451d,0x47dd487c,0x4af74aa0,
0x4abd4b11,0x48504780,0x458146b5,0x4b834b43,0x4bf84c00,0x3d970000,0x49a64a1f,0x49aa4927,0x4bba4be1,0x44264191,0x48944922,0x4a904a23,
0x4b3f4b84,0x46c6457c,0x46bb47f9,0x4b424af0,0x4a8c4aed,0x48994802,0x441a4570,0x4bbc4b86,0x4bf74c00,0x3dfb0000,0x495449dc,0x49f84972,
0x4bb04bdc,0x446f41f4,0x482048bf,0x4adb4a71,0x4b244b72,0x473745da,0x458d46ee,0x4b814b36,0x4a584ac6,0x48e04842,0x41534420,0x4be34bbb,
0x4bf64c00,0x3e5f0000,0x48fd4996,0x4a4149ba,0x4ba54bd7,0x44b74257,0x474e4858,0x4b1e4ab8,0x4b074b5f,0x47a64637,0x445745da,0x4bb34b72,
0x4a214a9c,0x49244881,0x3cce4191,0x4bfa4be1,0x4bf54c00,0x3ec30000,0x48a3494d,0x4a8549fe,0x4b9a4bd2,0x44ff42b9,0x465447d8,0x4b594af9,
0x4ae84b4b,0x480a4693,0x423244bd,0x4bd94ba4,0x49e74a71,0x496648bf,0xb4523db0,0x4c004bf8,0x4bf34c00,0x3f270000,0x48454900,0x4ac44a3f,
0x4b8e4bcd,0x4546431b,0x455246f9,0x4b8b4b33,0x4ac74b36,0x484046ee,0x3f594334,0x4bf24bcb,0x49aa4a43,0x49a648fb,0xbef52a48,0x4bf44c00,
0x4bf24c00,0x3f8b0000,0x47c848b0,0x4afe4a7c,0x4b814bc7,0x458d437d,0x444b4614,0x4bb54b67,0x4aa54b20,0x48744748,0x388440e4,0x4bff4be8,
0x496b4a13,0x49e34935,0xc263bd4c,0x4bd74bf9,0x4bf04c00,0x3fef0000,0x46ff485d,0x4b324ab5,0x4b734bc1,0x45d443df,0x427c4529,0x4bd64b93,
0x4a814b08,0x48a847a1,0xb9b13d1a,0x4bfe4bf9,0x492949e1,0x4a1d496d,0xc49fc160,0x4ba94be3,0x4bef4c00,0x40290000,0x46314807,0x4b604ae9,
0x4b654bbb,0x461a4420,0x405b4438,0x4bed4bb7,0x4a5c4af0,0x48db47f9,0xbfef2e48,0x4bf04c00,0x48e549ad,0x4a5449a4,0xc602c408,0x4b6a4bbe,
0x4bed4c00,0x405b0000,0x455e475e,0x4b894b1a,0x4b574bb4,0x465f4451,0x3c6a4288,0x4bfb4bd5,0x4a354ad6,0x490c4828,0xc27cbc51,0x4bd64bfb,
0x489e4976,0x4a8949d8,0xc759c558,0x4b1b4b8a,0x4beb4c00,0x408d0000,0x448746aa,0x4bac4b46,0x4b474bad,0x46a44481,0x26484099,0x4c004beb,
0x4a0d4abc,0x493c4852,0xc47bc080,0x4bae4bec,0x4855493e,0x4aba4a0b,0xc850c69e,0x4abd4b49,0x4be94c00,0x40be0000,0x435945f1,0x4bc94b6e,
0x4b374ba6,0x46e844b1,0xbc383d4c,0x4bfc4bf9,0x49e34aa0,0x496b487c,0xc5b1c2d2,0x4b7a4bd1,0x480a4905,0x4ae84a3b,0xc8eac7d8,0x4a504af9,
0x4be74c00,0x40f00000,0x419e4534,0x4be04b91,0x4b274b9e,0x472c44e1,0xc042357f,0x4bee4c00,0x49b84a83,0x499948a6,0xc6ddc48d,0x4b3a4bab,
0x477a48c9,0x4b134a69,0xc979c881,0x49d64a9c,0x4be54c00,0x41220000,0x3fbd4475,0x4bf14baf,0x4b164b97,0x476f4511,0xc263b91b,0x4bd74bfe,
0x498b4a65,0x49c548ce,0xc7fec5ab,0x4aee4b7b,0x46dd488c,0x4b3a4a95,0xc9fcc90e,0x494f4a33,0x4be34c00,0x41530000,0x3c384365,0x4bfc4bc9,
0x4b044b8f,0x47b24540,0xc43ebe78,0x4bb74bf6,0x495d4a47,0x49f048f6,0xc889c6c1,0x4a974b41,0x463c484d,0x4b5e4abf,0xca73c992,0x48bc49be,
0x4be14c00,0x41850000,0x317f41db,0x4c004bdd,0x4af14b86,0x47f34570,0xc546c12e,0x4b8e4be5,0x492e4a27,0x4a19491d,0xc90cc7cd,0x4a354afc,
0x4599480d,0x4b7f4ae6,0xcadbca0b,0x4820493e,0x4bdf4c00,0x41b60000,0xb9b1404e,0x4bfe4bed,0x4ade4b7d,0x481a459f,0xc648c31b,0x4b5c4bcd,
0x48fd4a07,0x4a414943,0xc986c867,0x49c94aae,0x44f34796,0x4b9c4b0b,0xcb35ca78,0x46f448b5,0x4bdd4c00,0x41e80000,0xbe5f3d7e,0x4bf64bf8,
0x4acb4b74,0x483a45ce,0xc742c481,0x4b214bad,0x48cc49e5,0x4a674969,0xc9f8c8e2,0x49544a56,0x444b4710,0x4bb54b2e,0xcb7fcad9,0x45994822,
0x4bda4c00,0x42190000,0xc0f038b6,0x4be74bff,0x4ab64b6b,0x485a45fd,0xc81ac570,0x4ade4b86,0x489949c3,0x4a8c498d,0xca60c956,0x48d649f6,
0x43404687,0x4bcb4b4e,0xcbb8cb2e,0x44324710,0x4bd84c00,0x424b0000,0xc2adb248,0x4bd34c00,0x4aa24b62,0x487a462b,0xc88ec659,0x4a934b58,
0x4865499f,0x4ab049b1,0xcabdc9c3,0x4850498d,0x41e845fd,0x4bdd4b6b,0xcbe1cb74,0x418545ce,0x4bd64c00,0x427c0000,0xc432bbd9,0x4bb84bfc,
0x4a8c4b58,0x48994659,0xc8fdc73d,0x4a414b22,0x4830497b,0x4ad149d4,0xcb10ca27,0x4785491d,0x408d4570,0x4beb4b86,0xcbf9cbad,0x3d334481,
0x4bd34c00,0x42ad0000,0xc50bbf0e,0x4b984bf4,0x4a764b4e,0x48b74687,0xc966c80d,0x49e74ae6,0x47f34956,0x4af149f6,0xcb57ca83,0x465f48a6,
0x3e5f44e1,0x4bf64b9e,0xcc00cbd7,0xb17f4257,0x4bd04c00,0x42de0000,0xc5dfc115,0x4b714be6,0x4a604b43,0x48d646b5,0xc9c9c877,0x49864aa3,
0x47854930,0x4b104a17,0xcb92cad6,0x452f4828,0x3b434451,0x4bfd4bb4,0xcbf5cbf3,0xbe913f40,0x4bce4c00,0x430f0000,0xc6afc2a1,0x4b454bd4,
0x4a494b39,0x48f346e3,0xca25c8dd,0x491f4a5a,0x47154909,0x4b2c4a37,0xcbc0cb20,0x43eb4748,0x3311437d,0x4c004bc7,0xcbd9cbff,0xc2323711,
0x4bcb4c00,0x43400000,0xc77ac414,0x4b134bbc,0x4a314b2e,0x49114710,0xca7ac93e,0x48b24a0b,0x46a448e2,0x4b474a56,0xcbe2cb5f,0x416c4637,
0xb7764257,0x4bff4bd7,0xcbaccbfd,0xc487bb75,0x4bc84c00,0x43710000,0xc820c4d5,0x4adb4ba0,0x4a194b22,0x492e473d,0xcac7c99b,0x484049b5,
0x463148ba,0x4b604a74,0xcbf8cb95,0x3dc9451d,0xbc9c412e,0x4bfb4be5,0xcb6fcbeb,0xc5ebc099,0x4bc54c00,0x43a20000,0xc87fc593,0x4a9e4b80,
0x4a004b17,0x494a476a,0xcb0dc9f2,0x4790495b,0x45bc4891,0x4b784a92,0xcc00cbc0,0x317f43f7,0xbf594004,0x4bf24bf0,0xcb21cbca,0xc742c34c,
0x4bc24c00,0x43d30000,0xc8dbc64e,0x4a5c4b5a,0x49e74b0b,0x49664796,0xcb4aca43,0x469948fb,0x45464867,0x4b8e4aae,0xcbfbcbe0,0xbc6a41aa,
0xc1093db0,0x4be64bf8,0xcac4cb9b,0xc845c4f9,0x4bbf4c00,0x44020000,0xc933c705,0x4a154b30,0x49cd4aff,0x498247c2,0xcb7fca8e,0x45994896,
0x44cf483d,0x4ba14ac9,0xcbe9cbf5,0xc0be3eaa,0xc2633aac,0x4bd74bfd,0xca58cb5d,0xc8e0c642,0x4bbc4c00,0x441a0000,0xc986c7b7,0x49c94b02,
0x49b34af3,0x499d47ee,0xcbabcad3,0x4493482d,0x44574812,0x4bb34ae3,0xcbcbcbff,0xc34037da,0xc3ba33db,0x4bc34c00,0xc9dfcb11,0xc970c780,
0x4bb84c00,0x44320000,0xc9d6c832,0x49794ad0,0x49994ae6,0x49b8480d,0xcbcecb11,0x430f4780,0x43ba47cd,0x4bc34afc,0xcb9fcbfe,0xc4dbb97f,
0xc487b57f,0x4bac4c00,0xc958cab8,0xc9f4c858,0x4bb54c00,0x444b0000,0xca21c887,0x49244a99,0x497d4ad9,0x49d24822,0xcbe7cb49,0x40f0469e,
0x42c64775,0x4bd24b14,0xcb68cbf2,0xc60ebf72,0xc52fbb75,0x4b924bfd,0xc8c7ca52,0xca6bc8e7,0x4bb24c00,0x44630000,0xca67c8d8,0x48cc4a5e,
0x49624acc,0x49eb4838,0xcbf8cb79,0x3d9745b6,0x41cf471b,0x4bde4b2b,0xcb24cbdb,0xc737c20d,0xc5d4be14,0x4b734bf7,0xc82ac9e1,0xcad5c96d,
0x4bae4c00,0x447b0000,0xcaa9c927,0x486f4a1f,0x49464abf,0x4a04484d,0xcc00cba2,0x351b44c9,0x40d746c1,0x4be84b41,0xcad5cbb9,0xc82ac42c,
0xc676c036,0x4b524bee,0xc70ac964,0xcb2fc9e9,0x4bab4c00,0x44930000,0xcae5c972,0x480f49dc,0x49294ab1,0x4a1d4862,0xcbfecbc4,0xba1643ae,
0x3fbd4665,0x4bf14b55,0xca7acb8c,0xc8b2c54c,0xc715c160,0x4b2c4be3,0xc5b1c8dd,0xcb7aca5a,0x4ba74c00,0x44ab0000,0xcb1bc9ba,0x47594996,
0x490c4aa3,0x4a354877,0xcbf2cbdf,0xbf5941c3,0x3dc94608,0x4bf84b69,0xca15cb55,0xc933c665,0xc7b2c288,0x4b044bd5,0xc44bc84d,0xcbb5cabf,
0x4ba34c00,0x44c30000,0xcb4cc9fe,0x468d494d,0x48ee4a95,0x4a4d488c,0xcbdecbf1,0xc1cf3fa4,0x3ba745ab,0x4bfc4b7b,0xc9a6cb14,0xc9aac775,
0xc825c3ae,0x4ad84bc4,0xc1b6c76a,0xcbdfcb17,0x4b9f4c00,0x44db0000,0xcb78ca3f,0x45bc4900,0x48d14a87,0x4a6448a0,0xcbc0cbfd,0xc3eb3b75,
0x3776454c,0x4bff4b8c,0xc92ecac9,0xca19c83d,0xc86fc469,0x4aa94bb1,0xbd97c62b,0xcbf8cb62,0x4b9c4c00,0x44f30000,0xcb9eca7c,0x44e748b0,
0x48b24a78,0x4a7a48b5,0xcb9acc00,0xc4ffaa48,0xa64844ed,0x4c004b9d,0xc8adca74,0xca7ec8ba,0xc8b7c4f9,0x4a764b9b,0x2cb6c4e1,0xcc00cb9e,
0x4b984c00,0x450b0000,0xcbbdcab5,0x440e485d,0x48944a69,0x4a9048c9,0xcb6acbfc,0xc602bc1f,0xb81f448d,0x4bff4bab,0xc825ca17,0xcad8c930,
0xc8fdc587,0x4a414b82,0x3e2dc31b,0xcbf6cbcd,0x4b944c00,0x45230000,0xcbd7cae9,0x42634807,0x48744a5a,0x4aa548dd,0xcb32cbf0,0xc6ffc004,
0xbc06442c,0x4bfc4bb9,0xc72cc9b1,0xcb27c99f,0xc941c614,0x4a094b67,0x4201c067,0xcbdccbed,0x4b904c00,0x453a0000,0xcbeacb1a,0x40a6475e,
0x48554a4b,0x4aba48f1,0xcaf1cbdc,0xc7f3c1f4,0xbdfb4396,0x4bf74bc6,0xc602c943,0xcb6aca07,0xc982c69e,0x49cd4b49,0x446fbaac,0xcbb0cbfd,
0x4b8b4c00,0x45520000,0xcbf8cb46,0x3dc946aa,0x48354a3b,0x4ace4905,0xcaa9cbc1,0xc86fc3df,0xbfef42d2,0x4bf04bd1,0xc4cfc8ce,0xcba1ca65,
0xc9c0c726,0x49904b28,0x45d43852,0xcb73cbff,0x4b874c00,0x456a0000,0xcbffcb6e,0x388445f1,0x48154a2b,0x4ae14918,0xca58cb9e,0xc8e0c4e1,
0xc0f0420d,0x4be74bdb,0xc328c852,0xcbcccabc,0xc9fcc7ac,0x494f4b05,0x472c3fa4,0xcb27cbf1,0x4b834c00,0x45810000,0xcc00cb91,0xb51b4534,
0x47e84a1b,0x4af4492b,0xca00cb74,0xc94ac5ce,0xc1e84147,0x4bdd4be4,0xc0a6c7a1,0xcbeacb08,0xca35c817,0x490c4ae0,0x483a4288,0xcacbcbd5,
0x4b7f4c00,0x45990000,0xcbfacbaf,0xbcce4475,0x47a64a0b,0x4b07493e,0xc9a1cb43,0xc9afc6b5,0xc2de4080,0x4bd04bec,0xbc38c693,0xcbfccb4b,
0xca6bc858,0x48c74ab8,0x48d64499,0xca60cbaa,0x4b7a4c00,0x45b10000,0xcbefcbc9,0xc0294365,0x476449fa,0x4b184951,0xc93ccb0b,0xca0dc796,
0xc3d33f72,0x4bc24bf2,0x3311c57c,0xcc00cb84,0xca9ec896,0x487f4a8e,0x496645e5,0xc9e7cb70,0x4b764c00,0x45c80000,0xcbddcbdd,0xc1e841db,
0x472149e9,0x4b2a4964,0xc8d1cacc,0xca64c838,0xc4633de2,0x4bb24bf7,0x3dfbc45d,0xcbf7cbb2,0xcacec8d3,0x48354a62,0x49eb4726,0xc962cb28,
0x4b714c00,0x45df0000,0xcbc5cbed,0xc3a2404e,0x46dd49d8,0x4b3a4976,0xc85fca87,0xcab3c8a0,0xc4db3c51,0x4b9f4bfb,0x4185c26f,0xcbe1cbd6,
0xcafbc90e,0x47d24a33,0x4a64482d,0xc8d1cad3,0x4b6c4c00,0x45f70000,0xcba7cbf8,0xc4ab3d7e,0x469949c7,0x4b4a4989,0xc7d2ca3b,0xcafbc905,
0xc552397f,0x4b8b4bfe,0x4402c01d,0xcbbfcbef,0xcb24c948,0x47374a02,0x4ace48bf,0xc835ca71,0x4b684c00,0x460e0000,0xcb83cbff,0xc58138b6,
0x465449b5,0x4b59499b,0xc6ddc9e9,0xcb3ac964,0xc5c834b6,0x4b764c00,0x453abb11,0xcb90cbfd,0xcb4ac980,0x469949d0,0x4b2a4948,0xc721ca02,
0x2c002c00,0x2c002c00,0x2c002c00,0x2c002c00,0x2b642c00,0x261f29a8,0xa61f0000,0xab64a9a8,0x29a82c00,0xa9a80000,0xa9a8ac00,0x29a80000,
0x261f2c00,0xab64a9a8,0x2b640000,0xa61f29a8,0x2c00,0xac00,0x2c00,0xac00,0xa61f2c00,0x2b64a9a8,0xab640000,0x261f29a8,
0xa9a82c00,0x29a80000,0x29a8ac00,0xa9a80000,0xab642c00,0xa61f29a8,0x261f0000,0x2b64a9a8,0,0,0,0,
0x261f0000,0x2b6429a8,0x2b642c00,0x261f29a8,0x29a80000,0x29a82c00,0xa9a80000,0xa9a8ac00,0x2b640000,0xa61f29a8,0xa61fac00,0x2b6429a8,
0x2c000000,0xac000000,0x2c000000,0xac000000,0x2b640000,0xa61fa9a8,0xa61f2c00,0x2b64a9a8,0x29a80000,0x29a8ac00,0xa9a80000,0xa9a82c00,
0x261f0000,0x2b64a9a8,0x2b64ac00,0x261fa9a8,0xac002c00,0xac002c00,0xac002c00,0xac002c00,0xab642c00,0xa61f29a8,0x261f0000,0x2b64a9a8,
0xa9a82c00,0x29a80000,0x29a8ac00,0xa9a80000,0xa61f2c00,0x2b64a9a8,0xab640000,0x261f29a8,0x2c00,0xac00,0x2c00,0xac00,
0x261f2c00,0xab64a9a8,0x2b640000,0xa61f29a8,0x29a82c00,0xa9a80000,0xa9a8ac00,0x29a80000,0x2b642c00,0x261f29a8,0xa61f0000,0xab64a9a8,
0,0,0,0,0xa61f0000,0xab6429a8,0xab642c00,0xa61f29a8,0xa9a80000,0xa9a82c00,0x29a80000,0x29a8ac00,
0xab640000,0x261f29a8,0x261fac00,0xab6429a8,0xac000000,0x2c000000,0xac000000,0x2c000000,0xab640000,0x261fa9a8,0x261f2c00,0xab64a9a8,
0xa9a80000,0xa9a8ac00,0x29a80000,0x29a82c00,0xa61f0000,0xab64a9a8,0xab64ac00,0xa61fa9a8,0,0,0,0,
0xa61f0000,0xab64a9a8,0xab64ac00,0xa61fa9a8,0xa9a80000,0xa9a8ac00,0x29a80000,0x29a82c00,0xab640000,0x261fa9a8,0x261f2c00,0xab64a9a8,
0xac000000,0x2c000000,0xac000000,0x2c000000,0xab640000,0x261f29a8,0x261fac00,0xab6429a8,0xa9a80000,0xa9a82c00,0x29a80000,0x29a8ac00,
0xa61f0000,0xab6429a8,0xab642c00,0xa61f29a8,0x2c002c00,0x2c002c00,0x2c002c00,0x2c002c00,0x2b642c00,0x261f29a8,0xa61f0000,0xab64a9a8,
0x29a82c00,0xa9a80000,0xa9a8ac00,0x29a80000,0x261f2c00,0xab64a9a8,0x2b640000,0xa61f29a8,0x2c00,0xac00,0x2c00,0xac00,
0xa61f2c00,0x2b64a9a8,0xab640000,0x261f29a8,0xa9a82c00,0x29a80000,0x29a8ac00,0xa9a80000,0xab642c00,0xa61f29a8,0x261f0000,0x2b64a9a8,
0,0,0,0,0x261f0000,0x2b64a9a8,0x2b64ac00,0x261fa9a8,0x29a80000,0x29a8ac00,0xa9a80000,0xa9a82c00,
0x2b640000,0xa61fa9a8,0xa61f2c00,0x2b64a9a8,0x2c000000,0xac000000,0x2c000000,0xac000000,0x2b640000,0xa61f29a8,0xa61fac00,0x2b6429a8,
0x29a80000,0x29a82c00,0xa9a80000,0xa9a8ac00,0x261f0000,0x2b6429a8,0x2b642c00,0x261f29a8,0xac002c00,0xac002c00,0xac002c00,0xac002c00,
0xab642c00,0xa61f29a8,0x261f0000,0x2b64a9a8,0xa9a82c00,0x29a80000,0x29a8ac00,0xa9a80000,0xa61f2c00,0x2b64a9a8,0xab640000,0x261f29a8,
0x2c00,0xac00,0x2c00,0xac00,0x261f2c00,0xab64a9a8,0x2b640000,0xa61f29a8,0x29a82c00,0xa9a80000,0xa9a8ac00,0x29a80000,
0x2b642c00,0x261f29a8,0xa61f0000,0xab64a9a8,0x2c002c00,0x2c002c00,0x2c002c00,0x2c002c00,0xab64ac00,0xa61fa9a8,0x261f0000,0x2b6429a8,
0x29a82c00,0xa9a80000,0xa9a8ac00,0x29a80000,0xa61fac00,0x2b6429a8,0xab640000,0x261fa9a8,0x2c00,0xac00,0x2c00,0xac00,
0x261fac00,0xab6429a8,0x2b640000,0xa61fa9a8,0xa9a82c00,0x29a80000,0x29a8ac00,0xa9a80000,0x2b64ac00,0x261fa9a8,0xa61f0000,0xab6429a8,
0,0,0,0,0xa61f0000,0xab64a9a8,0xab64ac00,0xa61fa9a8,0x29a80000,0x29a82c00,0xa9a80000,0xa9a8ac00,
0xab640000,0x261fa9a8,0x261f2c00,0xab64a9a8,0x2c000000,0xac000000,0x2c000000,0xac000000,0xab640000,0x261f29a8,0x261fac00,0xab6429a8,
0x29a80000,0x29a8ac00,0xa9a80000,0xa9a82c00,0xa61f0000,0xab6429a8,0xab642c00,0xa61f29a8,0xac002c00,0xac002c00,0xac002c00,0xac002c00,
0x2b64ac00,0x261fa9a8,0xa61f0000,0xab6429a8,0xa9a82c00,0x29a80000,0x29a8ac00,0xa9a80000,0x261fac00,0xab6429a8,0x2b640000,0xa61fa9a8,
0x2c00,0xac00,0x2c00,0xac00,0xa61fac00,0x2b6429a8,0xab640000,0x261fa9a8,0x29a82c00,0xa9a80000,0xa9a8ac00,0x29a80000,
0xab64ac00,0xa61fa9a8,0x261f0000,0x2b6429a8,0,0,0,0,0x261f0000,0x2b64a9a8,0x2b64ac00,0x261fa9a8,
0xa9a80000,0xa9a82c00,0x29a80000,0x29a8ac00,0x2b640000,0xa61fa9a8,0xa61f2c00,0x2b64a9a8,0xac000000,0x2c000000,0xac000000,0x2c000000,
0x2b640000,0xa61f29a8,0xa61fac00,0x2b6429a8,0xa9a80000,0xa9a8ac00,0x29a80000,0x29a82c00,0x261f0000,0x2b6429a8,0x2b642c00,0x261f29a8,
0,0,0,0,0x261f0000,0x2b6429a8,0x2b642c00,0x261f29a8,0xa9a80000,0xa9a8ac00,0x29a80000,0x29a82c00,
0x2b640000,0xa61f29a8,0xa61fac00,0x2b6429a8,0xac000000,0x2c000000,0xac000000,0x2c000000,0x2b640000,0xa61fa9a8,0xa61f2c00,0x2b64a9a8,
0xa9a80000,0xa9a82c00,0x29a80000,0x29a8ac00,0x261f0000,0x2b64a9a8,0x2b64ac00,0x261fa9a8,0x2c002c00,0x2c002c00,0x2c002c00,0x2c002c00,
0xab64ac00,0xa61fa9a8,0x261f0000,0x2b6429a8,0x29a82c00,0xa9a80000,0xa9a8ac00,0x29a80000,0xa61fac00,0x2b6429a8,0xab640000,0x261fa9a8,
0x2c00,0xac00,0x2c00,0xac00,0x261fac00,0xab6429a8,0x2b640000,0xa61fa9a8,0xa9a82c00,0x29a80000,0x29a8ac00,0xa9a80000,
0x2b64ac00,0x261fa9a8,0xa61f0000,0xab6429a8,0,0,0,0,0xa61f0000,0xab6429a8,0xab642c00,0xa61f29a8,
0x29a80000,0x29a8ac00,0xa9a80000,0xa9a82c00,0xab640000,0x261f29a8,0x261fac00,0xab6429a8,0x2c000000,0xac000000,0x2c000000,0xac000000,
0xab640000,0x261fa9a8,0x261f2c00,0xab64a9a8,0x29a80000,0x29a82c00,0xa9a80000,0xa9a8ac00,0xa61f0000,0xab64a9a8,0xab64ac00,0xa61fa9a8,
0xac002c00,0xac002c00,0xac002c00,0xac002c00,0x2b64ac00,0x261fa9a8,0xa61f0000,0xab6429a8,0xa9a82c00,0x29a80000,0x29a8ac00,0xa9a80000,
0x261fac00,0xab6429a8,0x2b640000,0xa61fa9a8,0x2c00,0xac00,0x2c00,0xac00,0xa61fac00,0x2b6429a8,0xab640000,0x261fa9a8,
0x29a82c00,0xa9a80000,0xa9a8ac00,0x29a80000,0xab64ac00,0xa61fa9a8,0x261f0000,0x2b6429a8,0x2bd92c00,0x2aa72b64,0x287229a8,0x223e261f,
0x2aa72c00,0xa23e261f,0xabd9a9a8,0xa872ab64,0x28722c00,0xabd9a61f,0x223ea9a8,0x2aa72b64,0x223e2c00,0xa872ab64,0x2aa729a8,0xabd9a61f,
0xa23e2c00,0x2872ab64,0xaaa729a8,0x2bd9a61f,0xa8722c00,0x2bd9a61f,0xa23ea9a8,0xaaa72b64,0xaaa72c00,0x223e261f,0x2bd9a9a8,0x2872ab64,
0xabd92c00,0xaaa72b64,0xa87229a8,0xa23e261f,0x223e0000,0x2872261f,0x2aa729a8,0x2bd92b64,0x28720000,0x2bd92b64,0x223e29a8,0xaaa7a61f,
0x2aa70000,0x223e2b64,0xabd9a9a8,0x2872a61f,0x2bd90000,0xaaa7261f,0x2872a9a8,0xa23e2b64,0x2bd90000,0xaaa7a61f,0x287229a8,0xa23eab64,
0x2aa70000,0x223eab64,0xabd929a8,0x2872261f,0x28720000,0x2bd9ab64,0x223ea9a8,0xaaa7261f,0x223e0000,0x2872a61f,0x2aa7a9a8,0x2bd9ab64,
0xabd92c00,0xaaa72b64,0xa87229a8,0xa23e261f,0xaaa72c00,0x223e261f,0x2bd9a9a8,0x2872ab64,0xa8722c00,0x2bd9a61f,0xa23ea9a8,0xaaa72b64,
0xa23e2c00,0x2872ab64,0xaaa729a8,0x2bd9a61f,0x223e2c00,0xa872ab64,0x2aa729a8,0xabd9a61f,0x28722c00,0xabd9a61f,0x223ea9a8,0x2aa72b64,
0x2aa72c00,0xa23e261f,0xabd9a9a8,0xa872ab64,0x2bd92c00,0x2aa72b64,0x287229a8,0x223e261f,0xa23e0000,0xa872261f,0xaaa729a8,0xabd92b64,
0xa8720000,0xabd92b64,0xa23e29a8,0x2aa7a61f,0xaaa70000,0xa23e2b64,0x2bd9a9a8,0xa872a61f,0xabd90000,0x2aa7261f,0xa872a9a8,0x223e2b64,
0xabd90000,0x2aa7a61f,0xa87229a8,0x223eab64,0xaaa70000,0xa23eab64,0x2bd929a8,0xa872261f,0xa8720000,0xabd9ab64,0xa23ea9a8,0x2aa7261f,
0xa23e0000,0xa872a61f,0xaaa7a9a8,0xabd9ab64,0xa23e0000,0xa872a61f,0xaaa7a9a8,0xabd9ab64,0xa8720000,0xabd9ab64,0xa23ea9a8,0x2aa7261f,
0xaaa70000,0xa23eab64,0x2bd929a8,0xa872261f,0xabd90000,0x2aa7a61f,0xa87229a8,0x223eab64,0xabd90000,0x2aa7261f,0xa872a9a8,0x223e2b64,
0xaaa70000,0xa23e2b64,0x2bd9a9a8,0xa872a61f,0xa8720000,0xabd92b64,0xa23e29a8,0x2aa7a61f,0xa23e0000,0xa872261f,0xaaa729a8,0xabd92b64,
0x2bd92c00,0x2aa72b64,0x287229a8,0x223e261f,0x2aa72c00,0xa23e261f,0xabd9a9a8,0xa872ab64,0x28722c00,0xabd9a61f,0x223ea9a8,0x2aa72b64,
0x223e2c00,0xa872ab64,0x2aa729a8,0xabd9a61f,0xa23e2c00,0x2872ab64,0xaaa729a8,0x2bd9a61f,0xa8722c00,0x2bd9a61f,0xa23ea9a8,0xaaa72b64,
0xaaa72c00,0x223e261f,0x2bd9a9a8,0x2872ab64,0xabd92c00,0xaaa72b64,0xa87229a8,0xa23e261f,0x223e0000,0x2872a61f,0x2aa7a9a8,0x2bd9ab64,
0x28720000,0x2bd9ab64,0x223ea9a8,0xaaa7261f,0x2aa70000,0x223eab64,0xabd929a8,0x2872261f,0x2bd90000,0xaaa7a61f,0x287229a8,0xa23eab64,
0x2bd90000,0xaaa7261f,0x2872a9a8,0xa23e2b64,0x2aa70000,0x223e2b64,0xabd9a9a8,0x2872a61f,0x28720000,0x2bd92b64,0x223e29a8,0xaaa7a61f,
0x223e0000,0x2872261f,0x2aa729a8,0x2bd92b64,0xabd92c00,0xaaa72b64,0xa87229a8,0xa23e261f,0xaaa72c00,0x223e261f,0x2bd9a9a8,0x2872ab64,
0xa8722c00,0x2bd9a61f,0xa23ea9a8,0xaaa72b64,0xa23e2c00,0x2872ab64,0xaaa729a8,0x2bd9a61f,0x223e2c00,0xa872ab64,0x2aa729a8,0xabd9a61f,
0x28722c00,0xabd9a61f,0x223ea9a8,0x2aa72b64,0x2aa72c00,0xa23e261f,0xabd9a9a8,0xa872ab64,0x2bd92c00,0x2aa72b64,0x287229a8,0x223e261f,
0xa23e0000,0xa872a61f,0xaaa7a9a8,0xabd9ab64,0x28720000,0x2bd92b64,0x223e29a8,0xaaa7a61f,0xaaa70000,0xa23eab64,0x2bd929a8,0xa872261f,
0x2bd90000,0xaaa7261f,0x2872a9a8,0xa23e2b64,0xabd90000,0x2aa7261f,0xa872a9a8,0x223e2b64,0x2aa70000,0x223eab64,0xabd929a8,0x2872261f,
0xa8720000,0xabd92b64,0xa23e29a8,0x2aa7a61f,0x223e0000,0x2872a61f,0x2aa7a9a8,0x2bd9ab64,0x2bd92c00,0x2aa72b64,0x287229a8,0x223e261f,
0xaaa7ac00,0x223ea61f,0x2bd929a8,0x28722b64,0x28722c00,0xabd9a61f,0x223ea9a8,0x2aa72b64,0xa23eac00,0x28722b64,0xaaa7a9a8,0x2bd9261f,
0xa23e2c00,0x2872ab64,0xaaa729a8,0x2bd9a61f,0x2872ac00,0xabd9261f,0x223e29a8,0x2aa7ab64,0xaaa72c00,0x223e261f,0x2bd9a9a8,0x2872ab64,
0x2bd9ac00,0x2aa7ab64,0x2872a9a8,0x223ea61f,0x223e0000,0x2872a61f,0x2aa7a9a8,0x2bd9ab64,0xa8720000,0xabd92b64,0xa23e29a8,0x2aa7a61f,
0x2aa70000,0x223eab64,0xabd929a8,0x2872261f,0xabd90000,0x2aa7261f,0xa872a9a8,0x223e2b64,0x2bd90000,0xaaa7261f,0x2872a9a8,0xa23e2b64,
0xaaa70000,0xa23eab64,0x2bd929a8,0xa872261f,0x28720000,0x2bd92b64,0x223e29a8,0xaaa7a61f,0xa23e0000,0xa872a61f,0xaaa7a9a8,0xabd9ab64,
0xabd92c00,0xaaa72b64,0xa87229a8,0xa23e261f,0x2aa7ac00,0xa23ea61f,0xabd929a8,0xa8722b64,0xa8722c00,0x2bd9a61f,0xa23ea9a8,0xaaa72b64,
0x223eac00,0xa8722b64,0x2aa7a9a8,0xabd9261f,0x223e2c00,0xa872ab64,0x2aa729a8,0xabd9a61f,0xa872ac00,0x2bd9261f,0xa23e29a8,0xaaa7ab64,
0x2aa72c00,0xa23e261f,0xabd9a9a8,0xa872ab64,0xabd9ac00,0xaaa7ab64,0xa872a9a8,0xa23ea61f,0xabd9ac00,0xaaa7ab64,0xa872a9a8,0xa23ea61f,
0x2aa72c00,0xa23e261f,0xabd9a9a8,0xa872ab64,0xa872ac00,0x2bd9261f,0xa23e29a8,0xaaa7ab64,0x223e2c00,0xa872ab64,0x2aa729a8,0xabd9a61f,
0x223eac00,0xa8722b64,0x2aa7a9a8,0xabd9261f,0xa8722c00,0x2bd9a61f,0xa23ea9a8,0xaaa72b64,0x2aa7ac00,0xa23ea61f,0xabd929a8,0xa8722b64,
0xabd92c00,0xaaa72b64,0xa87229a8,0xa23e261f,0xa23e0000,0xa872a61f,0xaaa7a9a8,0xabd9ab64,0x28720000,0x2bd92b64,0x223e29a8,0xaaa7a61f,
0xaaa70000,0xa23eab64,0x2bd929a8,0xa872261f,0x2bd90000,0xaaa7261f,0x2872a9a8,0xa23e2b64,0xabd90000,0x2aa7261f,0xa872a9a8,0x223e2b64,
0x2aa70000,0x223eab64,0xabd929a8,0x2872261f,0xa8720000,0xabd92b64,0xa23e29a8,0x2aa7a61f,0x223e0000,0x2872a61f,0x2aa7a9a8,0x2bd9ab64,
0x2bd9ac00,0x2aa7ab64,0x2872a9a8,0x223ea61f,0xaaa72c00,0x223e261f,0x2bd9a9a8,0x2872ab64,0x2872ac00,0xabd9261f,0x223e29a8,0x2aa7ab64,
0xa23e2c00,0x2872ab64,0xaaa729a8,0x2bd9a61f,0xa23eac00,0x28722b64,0xaaa7a9a8,0x2bd9261f,0x28722c00,0xabd9a61f,0x223ea9a8,0x2aa72b64,
0xaaa7ac00,0x223ea61f,0x2bd929a8,0x28722b64,0x2bd92c00,0x2aa72b64,0x287229a8,0x223e261f,0x223e0000,0x2872a61f,0x2aa7a9a8,0x2bd9ab64,
0xa8720000,0xabd92b64,0xa23e29a8,0x2aa7a61f,0x2aa70000,0x223eab64,0xabd929a8,0x2872261f,0xabd90000,0x2aa7261f,0xa872a9a8,0x223e2b64,
0x2bd90000,0xaaa7261f,0x2872a9a8,0xa23e2b64,0xaaa70000,0xa23eab64,0x2bd929a8,0xa872261f,0x28720000,0x2bd92b64,0x223e29a8,0xaaa7a61f,
0xa23e0000,0xa872a61f,0xaaa7a9a8,0xabd9ab64,0x27fe2800,0x96480000,0x273b2764,0xa2d7a21f,0x27ea27f6,0x9cb29a46,0x26dd270e,0xa41da38b,
0x27c327d9,0x9fc69e3e,0x266d26a7,0xa4c4a472,0x278827a8,0xa164a0a5,0x25ed262f,0xa55fa513,0x27c32800,0x9fc60000,0xa4c4a21f,0xa66da764,
0x25ed270e,0xa55fa38b,0xa73ba62f,0xa2d7a513,0x21642472,0xa788a6a7,0xa7fea7d9,0x16489e3e,0x9cb21a46,0xa7eaa7f6,0xa6dda7a8,0x241d20a5,
0x273b2800,0xa2d70000,0xa55fa764,0x25ed221f,0x1fc62513,0xa7c3a62f,0x1cb2a0a5,0x27ea27a8,0xa4c49e3e,0xa66da7d9,0x26dd2472,0x241d26a7,
0xa7fea70e,0x9648a38b,0x278827f6,0xa1641a46,0x266d2800,0xa4c40000,0x26dd221f,0x241d2764,0xa16420a5,0xa788a7a8,0x25ed27f6,0xa55f9a46,
0xa7fea6a7,0x1648a472,0xa2d71e3e,0xa73ba7d9,0x9fc6a62f,0x27c32513,0xa7eaa70e,0x1cb2a38b,0x255f2800,0xa5ed0000,0x21642764,0xa788a21f,
0xa66d9a46,0xa4c4a7f6,0xa7c3a38b,0x9fc6a70e,0xa41da7d9,0x26dd1e3e,0x9cb2a6a7,0x27ea2472,0x273b20a5,0x22d727a8,0x27fe2513,0x1648262f,
0x241d2800,0xa6dd0000,0xa7eaa21f,0x9cb2a764,0xa7fea38b,0x9648a70e,0x2164a513,0x2788262f,0x22d7a472,0x273b26a7,0x255f27d9,0xa5ed1e3e,
0x24c427f6,0xa66d1a46,0xa7c3a0a5,0x9fc6a7a8,0x21642800,0xa7880000,0x1648a764,0x27fe221f,0xa6dda62f,0x241da513,0x24c427a8,0xa66d20a5,
0x27ea1e3e,0x1cb227d9,0xa7c3a472,0x1fc6a6a7,0xa55f238b,0xa5eda70e,0x273b9a46,0x22d727f6,0x1cb22800,0xa7ea0000,0x27c3221f,0x9fc62764,
0xa2d7a7a8,0x273ba0a5,0xa7fe9a46,0x9648a7f6,0x255f26a7,0xa5ed2472,0x27889e3e,0x216427d9,0xa6dda513,0x241da62f,0xa66d238b,0xa4c4a70e,
0x96482800,0xa7fe0000,0xa2d72764,0xa73ba21f,0x1cb2a7f6,0x27ea1a46,0x241da70e,0x26dd238b,0x9fc627d9,0xa7c39e3e,0xa4c426a7,0xa66da472,
0x2164a7a8,0x278820a5,0x255fa62f,0x25ed2513,0x9fc62800,0xa7c30000,0xa66da21f,0x24c4a764,0x255fa70e,0x25ed238b,0x22d7262f,0xa73b2513,
0xa7882472,0xa164a6a7,0x1648a7d9,0x27fe9e3e,0x27ea9a46,0x9cb227f6,0xa41d27a8,0xa6dda0a5,0xa2d72800,0xa73b0000,0x25eda764,0x255f221f,
0x27c3a513,0x1fc6262f,0xa7ea20a5,0x1cb2a7a8,0xa66d9e3e,0x24c4a7d9,0x241d2472,0xa6dd26a7,0x1648270e,0xa7fe238b,0x2164a7f6,0x27889a46,
0xa4c42800,0xa66d0000,0x241d221f,0xa6dd2764,0x2788a0a5,0xa16427a8,0x255fa7f6,0x25ed1a46,0x1648a6a7,0x27fea472,0xa73b1e3e,0x22d7a7d9,
0xa7c3262f,0x9fc6a513,0x9cb2270e,0xa7ea238b,0xa5ed2800,0xa55f0000,0xa7882764,0xa164a21f,0x24c41a46,0xa66d27f6,0x1fc6238b,0xa7c3270e,
0x26dda7d9,0x241d1e3e,0x27eaa6a7,0x1cb22472,0xa2d7a0a5,0x273ba7a8,0x9648a513,0x27fea62f,0xa6dd2800,0xa41d0000,0x9cb2a21f,0x27eaa764,
0x1648238b,0xa7fe270e,0xa7882513,0x2164a62f,0x273ba472,0xa2d726a7,0xa5ed27d9,0xa55f1e3e,0x266da7f6,0x24c49a46,0x1fc620a5,0xa7c327a8,
0xa7882800,0xa1640000,0x27fea764,0x9648221f,0xa41d262f,0xa6dd2513,0x266da7a8,0x24c4a0a5,0x1cb21e3e,0xa7ea27d9,0x1fc6a472,0x27c3a6a7,
0x25eda38b,0xa55f270e,0xa2d71a46,0x273ba7f6,0xa7ea2800,0x9cb20000,0x9fc6221f,0xa7c32764,0xa73b27a8,0xa2d720a5,0x16481a46,0xa7fe27f6,
0xa5ed26a7,0xa55f2472,0x21649e3e,0xa78827d9,0xa41d2513,0xa6dd262f,0x24c4a38b,0xa66d270e,0xa7fe2800,0x16480000,0xa73b2764,0x22d7a21f,
0xa7ea27f6,0x1cb29a46,0xa6dd270e,0x241da38b,0xa7c327d9,0x1fc69e3e,0xa66d26a7,0x24c4a472,0xa78827a8,0x2164a0a5,0xa5ed262f,0x255fa513,
0xa7c32800,0x1fc60000,0x24c4a21f,0x266da764,0xa5ed270e,0x255fa38b,0x273ba62f,0x22d7a513,0xa1642472,0x2788a6a7,0x27fea7d9,0x96489e3e,
0x1cb21a46,0x27eaa7f6,0x26dda7a8,0xa41d20a5,0xa73b2800,0x22d70000,0x255fa764,0xa5ed221f,0x9fc62513,0x27c3a62f,0x9cb2a0a5,0xa7ea27a8,
0x24c49e3e,0x266da7d9,0xa6dd2472,0xa41d26a7,0x27fea70e,0x1648a38b,0xa78827f6,0x21641a46,0xa66d2800,0x24c40000,0xa6dd221f,0xa41d2764,
0x216420a5,0x2788a7a8,0xa5ed27f6,0x255f9a46,0x27fea6a7,0x9648a472,0x22d71e3e,0x273ba7d9,0x1fc6a62f,0xa7c32513,0x27eaa70e,0x9cb2a38b,
0xa55f2800,0x25ed0000,0xa1642764,0x2788a21f,0x266d9a46,0x24c4a7f6,0x27c3a38b,0x1fc6a70e,0x241da7d9,0xa6dd1e3e,0x1cb2a6a7,0xa7ea2472,
0xa73b20a5,0xa2d727a8,0xa7fe2513,0x9648262f,0xa41d2800,0x26dd0000,0x27eaa21f,0x1cb2a764,0x27fea38b,0x1648a70e,0xa164a513,0xa788262f,
0xa2d7a472,0xa73b26a7,0xa55f27d9,0x25ed1e3e,0xa4c427f6,0x266d1a46,0x27c3a0a5,0x1fc6a7a8,0xa1642800,0x27880000,0x9648a764,0xa7fe221f,
0x26dda62f,0xa41da513,0xa4c427a8,0x266d20a5,0xa7ea1e3e,0x9cb227d9,0x27c3a472,0x9fc6a6a7,0x255f238b,0x25eda70e,0xa73b9a46,0xa2d727f6,
0x9cb22800,0x27ea0000,0xa7c3221f,0x1fc62764,0x22d7a7a8,0xa73ba0a5,0x27fe9a46,0x1648a7f6,0xa55f26a7,0x25ed2472,0xa7889e3e,0xa16427d9,
0x26dda513,0xa41da62f,0x266d238b,0x24c4a70e,0x16482800,0x27fe0000,0x22d72764,0x273ba21f,0x9cb2a7f6,0xa7ea1a46,0xa41da70e,0xa6dd238b,
0x1fc627d9,0x27c39e3e,0x24c426a7,0x266da472,0xa164a7a8,0xa78820a5,0xa55fa62f,0xa5ed2513,0x1fc62800,0x27c30000,0x266da21f,0xa4c4a764,
0xa55fa70e,0xa5ed238b,0xa2d7262f,0x273b2513,0x27882472,0x2164a6a7,0x9648a7d9,0xa7fe9e3e,0xa7ea9a46,0x1cb227f6,0x241d27a8,0x26dda0a5,
0x22d72800,0x273b0000,0xa5eda764,0xa55f221f,0xa7c3a513,0x9fc6262f,0x27ea20a5,0x9cb2a7a8,0x266d9e3e,0xa4c4a7d9,0xa41d2472,0x26dd26a7,
0x9648270e,0x27fe238b,0xa164a7f6,0xa7889a46,0x24c42800,0x266d0000,0xa41d221f,0x26dd2764,0xa788a0a5,0x216427a8,0xa55fa7f6,0xa5ed1a46,
0x9648a6a7,0xa7fea472,0x273b1e3e,0xa2d7a7d9,0x27c3262f,0x1fc6a513,0x1cb2270e,0x27ea238b,0x25ed2800,0x255f0000,0x27882764,0x2164a21f,
0xa4c41a46,0x266d27f6,0x9fc6238b,0x27c3270e,0xa6dda7d9,0xa41d1e3e,0xa7eaa6a7,0x9cb22472,0x22d7a0a5,0xa73ba7a8,0x1648a513,0xa7fea62f,
0x26dd2800,0x241d0000,0x1cb2a21f,0xa7eaa764,0x9648238b,0x27fe270e,0x27882513,0xa164a62f,0xa73ba472,0x22d726a7,0x25ed27d9,0x255f1e3e,
0xa66da7f6,0xa4c49a46,0x9fc620a5,0x27c327a8,0x27882800,0x21640000,0xa7fea764,0x1648221f,0x241d262f,0x26dd2513,0xa66da7a8,0xa4c4a0a5,
0x9cb21e3e,0x27ea27d9,0x9fc6a472,0xa7c3a6a7,0xa5eda38b,0x255f270e,0x22d71a46,0xa73ba7f6,0x27ea2800,0x1cb20000,0x1fc6221f,0x27c32764,
0x273b27a8,0x22d720a5,0x96481a46,0x27fe27f6,0x25ed26a7,0x255f2472,0xa1649e3e,0x278827d9,0x241d2513,0x26dd262f,0xa4c4a38b,0x266d270e,
0x255f25a8,0xa5eda5a8,0x2164221f,0xa788a764,0x24c42513,0xa66da62f,0x1fc620a5,0xa7c3a7a8,0x241d2472,0xa6dda6a7,0x1cb21e3e,0xa7eaa7d9,
0x22d7238b,0xa73ba70e,0x16481a46,0xa7fea7f6,0xa41da5a8,0x26dd25a8,0x27ea2764,0x1cb2221f,0x9648a0a5,0x27fe27a8,0x278827f6,0xa1649a46,
0x22d71e3e,0x273b27d9,0x255f26a7,0xa5eda472,0x266d2513,0x24c4262f,0x1fc6238b,0xa7c3a70e,0x216425a8,0xa788a5a8,0x1648a21f,0x27fe2764,
0xa41d9a46,0xa6dda7f6,0x266d238b,0x24c4270e,0xa7eaa6a7,0x9cb2a472,0x27c327d9,0x9fc61e3e,0xa5eda7a8,0x255f20a5,0x22d7262f,0xa73ba513,
0x9cb2a5a8,0x27ea25a8,0xa7c3a764,0x1fc6a21f,0x273b238b,0x22d7270e,0x9648a513,0x27fe262f,0x255f27d9,0xa5ed9e3e,0x27882472,0x216426a7,
0xa41d1a46,0xa6dda7f6,0x24c427a8,0xa66da0a5,0x964825a8,0xa7fea5a8,0xa2d7221f,0xa73ba764,0xa7eaa62f,0x1cb2a513,0xa6dda7a8,0x241da0a5,
0x1fc6a472,0x27c326a7,0x24c49e3e,0x266d27d9,0x2788270e,0xa164238b,0x25ed27f6,0xa55f1a46,0x1fc6a5a8,0x27c325a8,0x266d2764,0xa4c4221f,
0x25ed27a8,0xa55f20a5,0xa73b9a46,0xa2d7a7f6,0xa7889e3e,0xa164a7d9,0x1648a6a7,0x27fe2472,0x1cb2a62f,0x27ea2513,0x26dd270e,0xa41d238b,
0xa2d725a8,0xa73ba5a8,0x25eda21f,0x255f2764,0x9fc6a7f6,0x27c31a46,0x9cb2270e,0xa7eaa38b,0x266d26a7,0xa4c42472,0xa41da7d9,0x26dd9e3e,
0xa7fea0a5,0x9648a7a8,0x27882513,0xa164262f,0x24c4a5a8,0x266d25a8,0xa41da764,0x26dda21f,0xa164270e,0xa788a38b,0x25ed262f,0xa55f2513,
0x1648a7d9,0x27fe1e3e,0xa73ba472,0x22d7a6a7,0x1fc627f6,0xa7c31a46,0x27ea20a5,0x9cb227a8,0xa5ed25a8,0xa55fa5a8,0xa788221f,0xa164a764,
0x266da513,0x24c4262f,0x27c3a0a5,0x1fc627a8,0xa6dd2472,0xa41da6a7,0xa7ea1e3e,0x9cb2a7d9,0x273ba38b,0x22d7270e,0x27fe9a46,0x164827f6,
0x26dda5a8,0x241d25a8,0x1cb22764,0xa7ea221f,0xa7fe20a5,0x9648a7a8,0x2164a7f6,0x27881a46,0x273b1e3e,0xa2d727d9,0xa5ed26a7,0xa55fa472,
0xa4c4a513,0x266da62f,0x27c3a38b,0x1fc6270e,0xa78825a8,0xa164a5a8,0x27fea21f,0x96482764,0x26dd1a46,0xa41d27f6,0xa4c4a38b,0x266da70e,
0x9cb2a6a7,0x27eaa472,0x9fc627d9,0xa7c31e3e,0xa55f27a8,0xa5eda0a5,0x273ba62f,0x22d72513,0x27eaa5a8,0x1cb225a8,0x1fc6a764,0x27c3a21f,
0xa2d7a38b,0x273ba70e,0xa7fe2513,0x9648a62f,0xa5ed27d9,0xa55f9e3e,0x21642472,0xa78826a7,0x26dd9a46,0xa41d27f6,0x266da7a8,0x24c420a5,
0xa7fe25a8,0x1648a5a8,0xa73b221f,0x22d7a764,0x9cb2262f,0xa7ea2513,0xa41d27a8,0xa6dd20a5,0x27c3a472,0x9fc626a7,0x266d9e3e,0xa4c427d9,
0x2164a70e,0x2788a38b,0x255fa7f6,0x25ed9a46,0x27c3a5a8,0x9fc625a8,0xa4c42764,0xa66d221f,0x255fa7a8,0x25eda0a5,0x22d71a46,0xa73b27f6,
0xa1649e3e,0x2788a7d9,0x27fea6a7,0x96482472,0xa7ea262f,0x1cb2a513,0x241da70e,0x26dda38b,0xa73b25a8,0x22d7a5a8,0x255fa21f,0xa5ed2764,
0xa7c327f6,0x9fc69a46,0x27eaa70e,0x9cb2238b,0xa4c426a7,0xa66d2472,0x26dda7d9,0x241d9e3e,0x164820a5,0xa7fe27a8,0x2164a513,0x2788a62f,
0x266da5a8,0xa4c425a8,0x26dda764,0x241da21f,0x2788a70e,0xa164238b,0x255fa62f,0x25eda513,0x27fea7d9,0x96481e3e,0x22d7a472,0x273ba6a7,
0x27c3a7f6,0x1fc69a46,0x1cb2a0a5,0x27eaa7a8,0xa55f25a8,0x25eda5a8,0xa164221f,0x2788a764,0xa4c42513,0x266da62f,0x9fc620a5,0x27c3a7a8,
0xa41d2472,0x26dda6a7,0x9cb21e3e,0x27eaa7d9,0xa2d7238b,0x273ba70e,0x96481a46,0x27fea7f6,0x241da5a8,0xa6dd25a8,0xa7ea2764,0x9cb2221f,
0x1648a0a5,0xa7fe27a8,0xa78827f6,0x21649a46,0xa2d71e3e,0xa73b27d9,0xa55f26a7,0x25eda472,0xa66d2513,0xa4c4262f,0x9fc6238b,0x27c3a70e,
0xa16425a8,0x2788a5a8,0x9648a21f,0xa7fe2764,0x241d9a46,0x26dda7f6,0xa66d238b,0xa4c4270e,0x27eaa6a7,0x1cb2a472,0xa7c327d9,0x1fc61e3e,
0x25eda7a8,0xa55f20a5,0xa2d7262f,0x273ba513,0x1cb2a5a8,0xa7ea25a8,0x27c3a764,0x9fc6a21f,0xa73b238b,0xa2d7270e,0x1648a513,0xa7fe262f,
0xa55f27d9,0x25ed9e3e,0xa7882472,0xa16426a7,0x241d1a46,0x26dda7f6,0xa4c427a8,0x266da0a5,0x164825a8,0x27fea5a8,0x22d7221f,0x273ba764,
0x27eaa62f,0x9cb2a513,0x26dda7a8,0xa41da0a5,0x9fc6a472,0xa7c326a7,0xa4c49e3e,0xa66d27d9,0xa788270e,0x2164238b,0xa5ed27f6,0x255f1a46,
0x9fc6a5a8,0xa7c325a8,0xa66d2764,0x24c4221f,0xa5ed27a8,0x255f20a5,0x273b9a46,0x22d7a7f6,0x27889e3e,0x2164a7d9,0x9648a6a7,0xa7fe2472,
0x9cb2a62f,0xa7ea2513,0xa6dd270e,0x241d238b,0x22d725a8,0x273ba5a8,0xa5eda21f,0xa55f2764,0x1fc6a7f6,0xa7c31a46,0x1cb2270e,0x27eaa38b,
0xa66d26a7,0x24c42472,0x241da7d9,0xa6dd9e3e,0x27fea0a5,0x1648a7a8,0xa7882513,0x2164262f,0xa4c4a5a8,0xa66d25a8,0x241da764,0xa6dda21f,
0x2164270e,0x2788a38b,0xa5ed262f,0x255f2513,0x9648a7d9,0xa7fe1e3e,0x273ba472,0xa2d7a6a7,0x9fc627f6,0x27c31a46,0xa7ea20a5,0x1cb227a8,
0x25ed25a8,0x255fa5a8,0x2788221f,0x2164a764,0xa66da513,0xa4c4262f,0xa7c3a0a5,0x9fc627a8,0x26dd2472,0x241da6a7,0x27ea1e3e,0x1cb2a7d9,
0xa73ba38b,0xa2d7270e,0xa7fe9a46,0x964827f6,0xa6dda5a8,0xa41d25a8,0x9cb22764,0x27ea221f,0x27fe20a5,0x1648a7a8,0xa164a7f6,0xa7881a46,
0xa73b1e3e,0x22d727d9,0x25ed26a7,0x255fa472,0x24c4a513,0xa66da62f,0xa7c3a38b,0x9fc6270e,0x278825a8,0x2164a5a8,0xa7fea21f,0x16482764,
0xa6dd1a46,0x241d27f6,0x24c4a38b,0xa66da70e,0x1cb2a6a7,0xa7eaa472,0x1fc627d9,0x27c31e3e,0x255f27a8,0x25eda0a5,0xa73ba62f,0xa2d72513,
0xa7eaa5a8,0x9cb225a8,0x9fc6a764,0xa7c3a21f,0x22d7a38b,0xa73ba70e,0x27fe2513,0x1648a62f,0x25ed27d9,0x255f9e3e,0xa1642472,0x278826a7,
0xa6dd9a46,0x241d27f6,0xa66da7a8,0xa4c420a5,0x27fe25a8,0x9648a5a8,0x273b221f,0xa2d7a764,0x1cb2262f,0x27ea2513,0x241d27a8,0x26dd20a5,
0xa7c3a472,0x1fc626a7,0xa66d9e3e,0x24c427d9,0xa164a70e,0xa788a38b,0xa55fa7f6,0xa5ed9a46,0xa7c3a5a8,0x1fc625a8,0x24c42764,0x266d221f,
0xa55fa7a8,0xa5eda0a5,0xa2d71a46,0x273b27f6,0x21649e3e,0xa788a7d9,0xa7fea6a7,0x16482472,0x27ea262f,0x9cb2a513,0xa41da70e,0xa6dda38b,
0x273b25a8,0xa2d7a5a8,0xa55fa21f,0x25ed2764,0x27c327f6,0x1fc69a46,0xa7eaa70e,0x1cb2238b,0x24c426a7,0x266d2472,0xa6dda7d9,0xa41d9e3e,
0x964820a5,0x27fe27a8,0xa164a513,0xa788a62f,0xa66da5a8,0x24c425a8,0xa6dda764,0xa41da21f,0xa788a70e,0x2164238b,0xa55fa62f,0xa5eda513,
0xa7fea7d9,0x16481e3e,0xa2d7a472,0xa73ba6a7,0xa7c3a7f6,0x9fc69a46,0x9cb2a0a5,0xa7eaa7a8,
};

#define PROF(slot) do {} while (0)
#define PROF3(slot) do {} while (0)
#define PROF2(slot) do {} while (0)

__device__ __forceinline__ uint32_t smem_u32(const void* p) { return (uint32_t)__cvta_generic_to_shared(p); }

__device__ __forceinline__ void mbar_init(uint32_t a, uint32_t c) {
  asm volatile("mbarrier.init.shared::cta.b64 [%0], %1;\n" ::"r"(a), "r"(c) : "memory");
}
__device__ __forceinline__ void mbar_expect_tx(uint32_t a, uint32_t bytes) {
  asm volatile("mbarrier.arrive.expect_tx.shared::cta.b64 _, [%0], %1;\n" ::"r"(a), "r"(bytes) : "memory");
}
__device__ __forceinline__ void mbar_arrive_cluster(uint32_t cluster_addr) {
  asm volatile("mbarrier.arrive.shared::cluster.b64 _, [%0];\n" ::"r"(cluster_addr) : "memory");
}
__device__ __forceinline__ void mbar_arrive_cluster_n(uint32_t cluster_addr, uint32_t n) {
  asm volatile("mbarrier.arrive.shared::cluster.b64 _, [%0], %1;\n" ::"r"(cluster_addr), "r"(n) : "memory");
}
__device__ __forceinline__ bool mbar_try(uint32_t a, uint32_t parity) {
  uint32_t ok;
  asm volatile("{\n.reg .pred p;\nmbarrier.try_wait.parity.shared::cta.b64 p, [%1], %2;\nselp.u32 %0, 1, 0, p;\n}\n"
               : "=r"(ok) : "r"(a), "r"(parity) : "memory");
  return ok;
}
__device__ __forceinline__ void mbar_wait(uint32_t a, uint32_t parity) {
  if (mbar_try(a, parity)) return;
#pragma unroll 1
  for (int n = 0; n < SPIN_LIMIT; n++)
    if (mbar_try(a, parity)) break;
}
__device__ __forceinline__ void mbar_wait_idle(uint32_t a, uint32_t parity) {
#pragma unroll 1
  for (int n = 0; n < SPIN_LIMIT; n++) {
    uint32_t ok;
    asm volatile("{\n.reg .pred p;\nmbarrier.try_wait.parity.shared::cta.b64 p, [%1], %2, %3;\nselp.u32 %0, 1, 0, p;\n}\n"
                 : "=r"(ok) : "r"(a), "r"(parity), "r"(4000) : "memory");
    if (ok) break;
  }
}
__device__ __forceinline__ bool elect_one() {
  uint32_t p;
  asm volatile("{\n.reg .pred P;\nelect.sync _|P, 0xffffffff;\nselp.u32 %0, 1, 0, P;\n}\n" : "=r"(p));
  return p;
}
__device__ __forceinline__ uint32_t mapa(uint32_t a, uint32_t rank) {
  uint32_t r;
  asm volatile("mapa.shared::cluster.u32 %0, %1, %2;\n" : "=r"(r) : "r"(a), "r"(rank));
  return r;
}
__device__ __forceinline__ void nb_sync(int id, int n) { asm volatile("bar.sync %0, %1;\n" ::"r"(id), "r"(n) : "memory"); }
__device__ __forceinline__ void nb_arrive(int id, int n) { asm volatile("bar.arrive %0, %1;\n" ::"r"(id), "r"(n) : "memory"); }
__device__ __forceinline__ void cluster_sync_all() {
  asm volatile("barrier.cluster.arrive.relaxed.aligned;\nbarrier.cluster.wait.aligned;\n" ::: "memory");
}
__device__ __forceinline__ void fence_async_smem() { asm volatile("fence.proxy.async.shared::cta;\n" ::: "memory"); }
__device__ __forceinline__ void fence_async_all() { asm volatile("fence.proxy.async.global;\n" ::: "memory"); }

__device__ __forceinline__ void tma_load_3d(uint32_t dst, const CUtensorMap* tm, uint32_t bar, int c0, int c1, int c2) {
  asm volatile(
      "cp.async.bulk.tensor.3d.shared::cluster.global.mbarrier::complete_tx::bytes [%0], [%1, {%3, %4, %5}], [%2];\n"
      ::"r"(dst), "l"(tm), "r"(bar), "r"(c0), "r"(c1), "r"(c2) : "memory");
}
__device__ __forceinline__ void tma_load_4d(uint32_t dst, const CUtensorMap* tm, uint32_t bar, int c0, int c1, int c2, int c3) {
  asm volatile(
      "cp.async.bulk.tensor.4d.shared::cluster.global.mbarrier::complete_tx::bytes [%0], [%1, {%3, %4, %5, %6}], [%2];\n"
      ::"r"(dst), "l"(tm), "r"(bar), "r"(c0), "r"(c1), "r"(c2), "r"(c3) : "memory");
}
__device__ __forceinline__ void tma_load_3d_mc(uint32_t dst, const CUtensorMap* tm, uint32_t bar, int c0, int c1, int c2) {
  asm volatile(
      "cp.async.bulk.tensor.3d.shared::cluster.global.mbarrier::complete_tx::bytes.multicast::cluster [%0], [%1, {%3, %4, %5}], [%2], %6;\n"
      ::"r"(dst), "l"(tm), "r"(bar), "r"(c0), "r"(c1), "r"(c2), "h"((uint16_t)3) : "memory");
}
__device__ __forceinline__ void tma_load_5d(uint32_t dst, const CUtensorMap* tm, uint32_t bar, int c0, int c4) {
  asm volatile(
      "cp.async.bulk.tensor.5d.shared::cluster.global.mbarrier::complete_tx::bytes [%0], [%1, {%3, %5, %5, %5, %4}], [%2];\n"
      ::"r"(dst), "l"(tm), "r"(bar), "r"(c0), "r"(c4), "r"(0) : "memory");
}
__device__ __forceinline__ void bulk_load(uint32_t dst, const void* src, uint32_t bytes, uint32_t bar) {
  asm volatile("cp.async.bulk.shared::cluster.global.mbarrier::complete_tx::bytes [%0], [%1], %2, [%3];\n"
               ::"r"(dst), "l"(src), "r"(bytes), "r"(bar) : "memory");
}
__device__ __forceinline__ void bulk_commit() { asm volatile("cp.async.bulk.commit_group;\n" ::: "memory"); }
__device__ __forceinline__ void bulk_wait0() { asm volatile("cp.async.bulk.wait_group 0;\n" ::: "memory"); }
__device__ __forceinline__ void prefetch_tmap(const CUtensorMap* tm) {
  asm volatile("prefetch.tensormap [%0];\n" ::"l"(tm) : "memory");
}

__device__ __forceinline__ void wg_fence() { asm volatile("wgmma.fence.sync.aligned;\n" ::: "memory"); }
__device__ __forceinline__ void wg_commit() { asm volatile("wgmma.commit_group.sync.aligned;\n" ::: "memory"); }
template <int N> __device__ __forceinline__ void wg_wait() {
  asm volatile("wgmma.wait_group.sync.aligned %0;\n" ::"n"(N) : "memory");
}
__device__ __forceinline__ uint64_t mkdesc(uint32_t addr, uint32_t lbo, uint32_t sbo, uint32_t swz) {
  return (uint64_t)((addr & 0x3FFFF) >> 4) | ((uint64_t)(lbo >> 4) << 16) | ((uint64_t)(sbo >> 4) << 32) |
         ((uint64_t)swz << 62);
}

#define R4(d, o) "+f"(d[o + 0]), "+f"(d[o + 1]), "+f"(d[o + 2]), "+f"(d[o + 3])
#define R8(d, o) R4(d, o), R4(d, o + 4)
#define R16(d, o) R8(d, o), R8(d, o + 8)
#define R32(d, o) R16(d, o), R16(d, o + 16)
#define R64(d, o) R32(d, o), R32(d, o + 32)

__device__ __forceinline__ void wgmma_n192(float (&d)[96], uint64_t da, uint64_t db, uint32_t acc) {
  asm volatile(
      "{\n.reg .pred p;\nsetp.ne.u32 p, %98, 0;\n"
      "wgmma.mma_async.sync.aligned.m64n192k16.f32.bf16.bf16 "
      "{%0,%1,%2,%3,%4,%5,%6,%7,%8,%9,%10,%11,%12,%13,%14,%15,%16,%17,%18,%19,%20,%21,%22,%23,%24,%25,%26,%27,%28,%29,%30,%31,"
      "%32,%33,%34,%35,%36,%37,%38,%39,%40,%41,%42,%43,%44,%45,%46,%47,%48,%49,%50,%51,%52,%53,%54,%55,%56,%57,%58,%59,%60,%61,%62,%63,"
      "%64,%65,%66,%67,%68,%69,%70,%71,%72,%73,%74,%75,%76,%77,%78,%79,%80,%81,%82,%83,%84,%85,%86,%87,%88,%89,%90,%91,%92,%93,%94,%95}, "
      "%96, %97, p, 1, 1, 0, 1;\n}\n"
      : R64(d, 0), R32(d, 64)
      : "l"(da), "l"(db), "r"(acc));
}
__device__ __forceinline__ void wgmma_n128(float (&d)[64], uint64_t da, uint64_t db, uint32_t acc) {
  asm volatile(
      "{\n.reg .pred p;\nsetp.ne.u32 p, %66, 0;\n"
      "wgmma.mma_async.sync.aligned.m64n128k16.f32.bf16.bf16 "
      "{%0,%1,%2,%3,%4,%5,%6,%7,%8,%9,%10,%11,%12,%13,%14,%15,%16,%17,%18,%19,%20,%21,%22,%23,%24,%25,%26,%27,%28,%29,%30,%31,"
      "%32,%33,%34,%35,%36,%37,%38,%39,%40,%41,%42,%43,%44,%45,%46,%47,%48,%49,%50,%51,%52,%53,%54,%55,%56,%57,%58,%59,%60,%61,%62,%63}, "
      "%64, %65, p, 1, 1, 0, 1;\n}\n"
      : R64(d, 0)
      : "l"(da), "l"(db), "r"(acc));
}
template <int N> __device__ __forceinline__ void fence_regs(float (&d)[N]) {
#pragma unroll
  for (int i = 0; i < N; i++) asm volatile("" : "+f"(d[i])::"memory");
}

__device__ __forceinline__ void mma16816(float (&d)[4], uint32_t a0, uint32_t a1, uint32_t a2, uint32_t a3, uint32_t b0,
                                         uint32_t b1) {
  asm("mma.sync.aligned.m16n8k16.row.col.f32.bf16.bf16.f32 {%0,%1,%2,%3}, {%4,%5,%6,%7}, {%8,%9}, {%0,%1,%2,%3};\n"
      : "+f"(d[0]), "+f"(d[1]), "+f"(d[2]), "+f"(d[3])
      : "r"(a0), "r"(a1), "r"(a2), "r"(a3), "r"(b0), "r"(b1));
}
__device__ __forceinline__ void mma16816_z(float (&d)[4], uint32_t a0, uint32_t a1, uint32_t a2, uint32_t a3, uint32_t b0,
                                           uint32_t b1) {
  asm("mma.sync.aligned.m16n8k16.row.col.f32.bf16.bf16.f32 {%0,%1,%2,%3}, {%4,%5,%6,%7}, {%8,%9}, {%10,%10,%10,%10};\n"
      : "=f"(d[0]), "=f"(d[1]), "=f"(d[2]), "=f"(d[3])
      : "r"(a0), "r"(a1), "r"(a2), "r"(a3), "r"(b0), "r"(b1), "f"(0.f));
}
__device__ __forceinline__ void ldsm4t(uint32_t (&r)[4], uint32_t a) {
  asm volatile("ldmatrix.sync.aligned.m8n8.x4.trans.shared.b16 {%0,%1,%2,%3}, [%4];\n"
               : "=r"(r[0]), "=r"(r[1]), "=r"(r[2]), "=r"(r[3]) : "r"(a) : "memory");
}
__device__ __forceinline__ void ldsm2t(uint32_t& r0, uint32_t& r1, uint32_t a) {
  asm volatile("ldmatrix.sync.aligned.m8n8.x2.trans.shared.b16 {%0,%1}, [%2];\n" : "=r"(r0), "=r"(r1) : "r"(a) : "memory");
}
__device__ __forceinline__ void st_async128(uint32_t a, uint32_t bar, uint32_t x, uint32_t y, uint32_t z, uint32_t w) {
  asm volatile("st.async.weak.shared::cluster.mbarrier::complete_tx::bytes.v4.b32 [%0], {%2,%3,%4,%5}, [%1];\n"
               ::"r"(a), "r"(bar), "r"(x), "r"(y), "r"(z), "r"(w) : "memory");
}
__device__ __forceinline__ void mbar_arrive(uint32_t a) {
  asm volatile("mbarrier.arrive.shared::cta.b64 _, [%0];\n" ::"r"(a) : "memory");
}
__device__ __forceinline__ void stsm4(uint32_t a, uint32_t r0, uint32_t r1, uint32_t r2, uint32_t r3) {
  asm volatile("stmatrix.sync.aligned.m8n8.x4.shared.b16 [%0], {%1,%2,%3,%4};\n"
               ::"r"(a), "r"(r0), "r"(r1), "r"(r2), "r"(r3) : "memory");
}
__device__ __forceinline__ void stsm4t(uint32_t a, uint32_t r0, uint32_t r1, uint32_t r2, uint32_t r3) {
  asm volatile("stmatrix.sync.aligned.m8n8.x4.trans.shared.b16 [%0], {%1,%2,%3,%4};\n"
               ::"r"(a), "r"(r0), "r"(r1), "r"(r2), "r"(r3) : "memory");
}
__device__ __forceinline__ uint2 lds64(uint32_t a) {
  uint2 v;
  asm volatile("ld.shared.v2.u32 {%0,%1}, [%2];\n" : "=r"(v.x), "=r"(v.y) : "r"(a));
  return v;
}
__device__ __forceinline__ uint4 lds128(uint32_t a) {
  uint4 v;
  asm volatile("ld.shared.v4.u32 {%0,%1,%2,%3}, [%4];\n" : "=r"(v.x), "=r"(v.y), "=r"(v.z), "=r"(v.w) : "r"(a) : "memory");
  return v;
}
__device__ __forceinline__ void sts128(uint32_t a, uint32_t x, uint32_t y, uint32_t z, uint32_t w) {
  asm volatile("st.shared.v4.u32 [%0], {%1,%2,%3,%4};\n" ::"r"(a), "r"(x), "r"(y), "r"(z), "r"(w) : "memory");
}
__device__ __forceinline__ uint32_t pack_bf16(float lo, float hi) {
  uint32_t r;
  asm("cvt.rn.bf16x2.f32 %0, %1, %2;\n" : "=r"(r) : "f"(hi), "f"(lo));
  return r;
}
__device__ __forceinline__ uint32_t bmul2(uint32_t a, uint32_t b) {
  uint32_t r;
  asm("mul.rn.bf16x2 %0, %1, %2;\n" : "=r"(r) : "r"(a), "r"(b));
  return r;
}
__device__ __forceinline__ uint32_t bmax2(uint32_t a, uint32_t b) {
  uint32_t r;
  asm("max.bf16x2 %0, %1, %2;\n" : "=r"(r) : "r"(a), "r"(b));
  return r;
}
__device__ __forceinline__ uint32_t bfma2(uint32_t a, uint32_t b, uint32_t c) {
  uint32_t r;
  asm("fma.rn.bf16x2 %0, %1, %2, %3;\n" : "=r"(r) : "r"(a), "r"(b), "r"(c));
  return r;
}
__device__ __forceinline__ uint32_t badd2(uint32_t a, uint32_t b) {
  uint32_t r;
  asm("add.rn.bf16x2 %0, %1, %2;\n" : "=r"(r) : "r"(a), "r"(b));
  return r;
}
__device__ __forceinline__ void prefetch_l2(const void* p) { asm volatile("prefetch.global.L2 [%0];\n" ::"l"(p)); }
__device__ __forceinline__ void cp_async16n(uint32_t dst, const void* src) {
  asm volatile("cp.async.cg.shared.global [%0], [%1], 16;\n" ::"r"(dst), "l"(src) : "memory");
}
__device__ __forceinline__ void cp_async16(uint32_t dst, const void* src, uint32_t srcbytes) {
  asm volatile("cp.async.cg.shared.global.L2::256B [%0], [%1], 16, %2;\n" ::"r"(dst), "l"(src), "r"(srcbytes) : "memory");
}
__device__ __forceinline__ uint32_t ld_acquire(const uint32_t* p) {
  uint32_t v;
  asm volatile("ld.acquire.gpu.global.u32 %0, [%1];\n" : "=r"(v) : "l"(p) : "memory");
  return v;
}
__device__ __forceinline__ uint32_t ld_relaxed(const uint32_t* p) {
  uint32_t v;
  asm volatile("ld.relaxed.gpu.global.u32 %0, [%1];\n" : "=r"(v) : "l"(p) : "memory");
  return v;
}
__device__ __forceinline__ void st_release(uint32_t* p, uint32_t v) {
  asm volatile("st.release.gpu.global.u32 [%0], %1;\n" ::"l"(p), "r"(v) : "memory");
}
__device__ __forceinline__ void wait_flag(const uint32_t* p, uint32_t want) {
  int n = 0;
  while (ld_relaxed(p) != want && ++n < SPIN_LIMIT) __nanosleep(40);
  (void)ld_acquire(p);
}

struct Params {
  const __nv_bfloat16* x;
  const __nv_bfloat16* w;
  const __nv_bfloat16* q;
  const __nv_bfloat16* k;
  const __nv_bfloat16* v;
  const __nv_bfloat16* shift_k;
  const __nv_bfloat16* ssm_k;
  const __nv_bfloat16* ssm_D;
  const __nv_bfloat16* wo;
  __nv_bfloat16* out;
};

__device__ __forceinline__ uint32_t lds32(uint32_t a) {
  uint32_t v;
  asm volatile("ld.shared.u32 %0, [%1];\n" : "=r"(v) : "r"(a));
  return v;
}
#define W4(d, o) "=f"(d[o + 0]), "=f"(d[o + 1]), "=f"(d[o + 2]), "=f"(d[o + 3])
#define W8(d, o) W4(d, o), W4(d, o + 4)
#define W16(d, o) W8(d, o), W8(d, o + 8)
#define U4(c, d, o) c(d[o + 0]), c(d[o + 1]), c(d[o + 2]), c(d[o + 3])
#define U8(c, d, o) U4(c, d, o), U4(c, d, o + 4)
#define U16(c, d, o) U8(c, d, o), U8(c, d, o + 8)
#define U32(c, d, o) U16(c, d, o), U16(c, d, o + 16)
#define D32 "{%0,%1,%2,%3,%4,%5,%6,%7,%8,%9,%10,%11,%12,%13,%14,%15,%16,%17,%18,%19,%20,%21,%22,%23,%24,%25,%26,%27,%28,%29,%30,%31}"
#define D16 "{%0,%1,%2,%3,%4,%5,%6,%7,%8,%9,%10,%11,%12,%13,%14,%15}"
#define D8 "{%0,%1,%2,%3,%4,%5,%6,%7}"
template <int ACC> __device__ __forceinline__ void hmma_n128t(uint32_t (&d)[32], const uint32_t (&a)[4], uint64_t db) {
  if (ACC)
    asm volatile("wgmma.mma_async.sync.aligned.m64n128k16.f16.f16.f16 " D32 ", {%32,%33,%34,%35}, %36, 1, 1, 1, 1;\n"
                 : U32("+r", d, 0) : "r"(a[0]), "r"(a[1]), "r"(a[2]), "r"(a[3]), "l"(db));
  else
    asm volatile("wgmma.mma_async.sync.aligned.m64n128k16.f16.f16.f16 " D32 ", {%32,%33,%34,%35}, %36, 0, 1, 1, 1;\n"
                 : U32("=r", d, 0) : "r"(a[0]), "r"(a[1]), "r"(a[2]), "r"(a[3]), "l"(db));
}
template <int ACC, int TB> __device__ __forceinline__ void hmma_n32(uint32_t (&d)[8], const uint32_t (&a)[4], uint64_t db) {
  if (ACC)
    asm volatile("wgmma.mma_async.sync.aligned.m64n32k16.f16.f16.f16 " D8 ", {%8,%9,%10,%11}, %12, 1, 1, 1, %13;\n"
                 : U8("+r", d, 0) : "r"(a[0]), "r"(a[1]), "r"(a[2]), "r"(a[3]), "l"(db), "n"(TB));
  else
    asm volatile("wgmma.mma_async.sync.aligned.m64n32k16.f16.f16.f16 " D8 ", {%8,%9,%10,%11}, %12, 0, 1, 1, %13;\n"
                 : U8("=r", d, 0) : "r"(a[0]), "r"(a[1]), "r"(a[2]), "r"(a[3]), "l"(db), "n"(TB));
}
template <int ACC> __device__ __forceinline__ void fmma_n32t(float (&d)[16], const uint32_t (&a)[4], uint64_t db) {
  if (ACC)
    asm volatile("wgmma.mma_async.sync.aligned.m64n32k16.f32.f16.f16 " D16 ", {%16,%17,%18,%19}, %20, 1, 1, 1, 1;\n"
                 : R16(d, 0) : "r"(a[0]), "r"(a[1]), "r"(a[2]), "r"(a[3]), "l"(db));
  else
    asm volatile("wgmma.mma_async.sync.aligned.m64n32k16.f32.f16.f16 " D16 ", {%16,%17,%18,%19}, %20, 0, 1, 1, 1;\n"
                 : W16(d, 0) : "r"(a[0]), "r"(a[1]), "r"(a[2]), "r"(a[3]), "l"(db));
}
template <int N> __device__ __forceinline__ void fence_regs(uint32_t (&d)[N]) {
#pragma unroll
  for (int i = 0; i < N; i++) asm volatile("" : "+r"(d[i])::"memory");
}
__device__ __forceinline__ uint32_t hmul(uint32_t a, uint32_t b) { uint32_t r; asm("mul.rn.f16x2 %0, %1, %2;\n" : "=r"(r) : "r"(a), "r"(b)); return r; }
__device__ __forceinline__ uint32_t hadd(uint32_t a, uint32_t b) { uint32_t r; asm("add.rn.f16x2 %0, %1, %2;\n" : "=r"(r) : "r"(a), "r"(b)); return r; }
__device__ __forceinline__ uint32_t hsub(uint32_t a, uint32_t b) { uint32_t r; asm("sub.rn.f16x2 %0, %1, %2;\n" : "=r"(r) : "r"(a), "r"(b)); return r; }
__device__ __forceinline__ uint32_t hfma(uint32_t a, uint32_t b, uint32_t c) { uint32_t r; asm("fma.rn.f16x2 %0, %1, %2, %3;\n" : "=r"(r) : "r"(a), "r"(b), "r"(c)); return r; }
__device__ __forceinline__ uint32_t hfnma(uint32_t a, uint32_t b, uint32_t c) {
  uint32_t r;
  asm("{\n.reg .b32 t;\nneg.f16x2 t, %1;\nfma.rn.f16x2 %0, t, %2, %3;\n}\n" : "=r"(r) : "r"(a), "r"(b), "r"(c));
  return r;
}
__device__ __forceinline__ uint32_t hrefl(uint32_t p, uint32_t s) {
  uint32_t r;
  asm("{\n.reg .b32 t;\nneg.f16x2 t, %2;\nfma.rn.f16x2 %0, %1, %3, t;\n}\n" : "=r"(r) : "r"(p), "r"(s), "r"(0x40004000u));
  return r;
}
__device__ __forceinline__ void bfly(uint32_t xr, uint32_t xi, uint32_t tr, uint32_t ti, uint32_t yr, uint32_t yi, uint32_t ur,
                                     uint32_t ui, uint32_t& sr, uint32_t& si, uint32_t& dr, uint32_t& di) {
  const uint32_t pr = hfnma(xi, ti, hmul(xr, tr)), pi = hfma(xi, tr, hmul(xr, ti));
  sr = hfnma(yi, ui, hfma(yr, ur, pr));
  si = hfma(yi, ur, hfma(yr, ui, pi));
  dr = hrefl(pr, sr);
  di = hrefl(pi, si);
}
template <int BH> __device__ __forceinline__ void fft_e1(const uint32_t (&d)[32], const uint32_t (&tw)[16], uint32_t (&a2)[2][2][4]) {
#pragma unroll
  for (int be = 0; be < 2; be++)
#pragma unroll
    for (int s = 0; s < 2; s++) {
      const int o = 16 * s + 8 * be + 2 * BH, p = 2 * BH;
      bfly(d[o], d[o + 1], tw[p], tw[p + 1], d[o + 4], d[o + 5], tw[p + 4], tw[p + 5], a2[be][0][s], a2[be][0][2 + s],
           a2[be][1][s], a2[be][1][2 + s]);
    }
}
__device__ __forceinline__ uint32_t hfms(uint32_t a, uint32_t b, uint32_t c) {
  uint32_t r;
  asm("{\n.reg .b32 t;\nneg.f16x2 t, %3;\nfma.rn.f16x2 %0, %1, %2, t;\n}\n" : "=r"(r) : "r"(a), "r"(b), "r"(c));
  return r;
}
template <int C, int J> __device__ __forceinline__ void fft_e2(const uint32_t (&d0)[8], const uint32_t (&d1)[8], uint32_t (&a3)[2][4]) {
  const uint32_t ur = d0[2 * J], ui = d0[4 + 2 * J], hr = d0[2 * J + 1], hi = d0[5 + 2 * J];
  const uint32_t vr = d1[2 * J], vi = d1[4 + 2 * J], gr = d1[2 * J + 1], gi = d1[5 + 2 * J];
  const uint32_t pr = hfnma(ui, hi, hmul(ur, hr)), pi = hfma(ui, hr, hmul(ur, hi));
  a3[0][2 + C] = pr;
  a3[0][C] = pi;
  a3[1][2 + C] = hfnma(vi, hi, hfma(vr, hr, hfnma(ui, gi, hfms(ur, gr, pi))));
  a3[1][C] = hfma(vi, hr, hfma(vr, hi, hfma(ui, gr, hfma(ur, gi, pr))));
}
__device__ __forceinline__ void fft_e3(const uint32_t (&d)[2][8], const uint32_t (&tw)[16], uint32_t zaddr) {
#pragma unroll
  for (int rho = 0; rho < 2; rho++) {
    uint32_t zr[4], zi[4];
#pragma unroll
    for (int nb = 0; nb < 4; nb++) {
      const uint32_t xi = d[nb >> 1][2 * (nb & 1) + rho], xr = d[nb >> 1][4 + 2 * (nb & 1) + rho];
      const uint32_t tr = tw[8 + 4 * rho + 2 * (nb & 1)], ti = tw[9 + 4 * rho + 2 * (nb & 1)];
      zr[nb] = hfnma(xi, ti, hmul(xr, tr));
      zi[nb] = hfma(xi, tr, hmul(xr, ti));
    }
    stsm4(zaddr + rho * 1024, zr[0], zr[1], zr[2], zr[3]);
    stsm4(zaddr + rho * 1024 + 512, zi[0], zi[1], zi[2], zi[3]);
  }
}
__device__ __forceinline__ float bf_lo(uint32_t v) {
  uint32_t r;
  asm("prmt.b32 %0, %1, 0, 0x1044;\n" : "=r"(r) : "r"(v));
  return __uint_as_float(r);
}
__device__ __forceinline__ float bf_hi(uint32_t v) { return __uint_as_float(v & 0xffff0000u); }
__device__ __forceinline__ float ex2(float x) {
  float r;
  asm("ex2.approx.ftz.f32 %0, %1;\n" : "=f"(r) : "f"(x));
  return r;
}
__device__ __forceinline__ float rcp(float x) {
  float r;
  asm("rcp.approx.ftz.f32 %0, %1;\n" : "=f"(r) : "f"(x));
  return r;
}

__device__ __forceinline__ int g2_a(int s) { return ((0xA1054 >> (4 * s)) & 15) * 16384; }
__device__ __forceinline__ int g2_b(int s) { return ((0xCDB32 >> (4 * s)) & 15) * 16384; }
static_assert(OFF_U == 10 * 16384 && OFF_H == 12 * 16384 && OFF_OP == 4 * 16384, "units");
__device__ __forceinline__ int g2_k(int hp, int i) {
  return i < 2 ? hp ^ 1 ^ i : i < 4 ? (hp & ~1) ^ i : ((hp & ~3) + i) & 15; }
__device__ __forceinline__ int y_slot(int wg, int it) {
  static_assert(T_B2 == T_TW + 8192 && T_A1 == T_B2 + 4096, "y slots");
  return OFF_T + T_TW + ((it + 3) & 3) * 4096 + wg * 2048;
}

__device__ __forceinline__ void to_arr(uint32_t (&d)[4], uint4 v) { d[0] = v.x; d[1] = v.y; d[2] = v.z; d[3] = v.w; }

__device__ __forceinline__ void attn_stage(uint32_t sb, int blk, int lane, const float (&acc)[96], uint32_t (&k1)[2][4]) {
  const int lr = lane & 7, lm = lane >> 3;
  const uint32_t base = sb + OFF_VP + (blk * 16 + lr + 8 * (lm & 1)) * 128;
#pragma unroll
  for (int i = 0; i < 8; i++) k1[i >> 2][i & 3] = pack_bf16(acc[34 + 4 * i], acc[35 + 4 * i]);
  const uint32_t kh = sb + OFF_KH + blk * 2048 + lane * 16;
  sts128(kh, k1[0][0], k1[0][1], k1[0][2], k1[0][3]);
  sts128(kh + 512, k1[1][0], k1[1][1], k1[1][2], k1[1][3]);
#pragma unroll
  for (int j = 0; j < 8; j += 2)
    stsm4(base + (((j + (lm >> 1)) ^ lr) << 4), pack_bf16(acc[64 + 4 * j], acc[65 + 4 * j]),
          pack_bf16(acc[66 + 4 * j], acc[67 + 4 * j]), pack_bf16(acc[68 + 4 * j], acc[69 + 4 * j]),
          pack_bf16(acc[70 + 4 * j], acc[71 + 4 * j]));
}
__device__ __forceinline__ void attn_pack(const float (&acc)[96], uint32_t (&qa)[2][8], uint32_t (&k0)[2][4]) {
#pragma unroll
  for (int hd = 0; hd < 2; hd++) {
#pragma unroll
    for (int i = 0; i < 8; i++) {
      asm volatile("cvt.rn.bf16x2.f32 %0, %1, %2;\n" : "=r"(qa[hd][i]) : "f"(acc[16 * hd + 2 * i + 1]), "f"(acc[16 * hd + 2 * i]));
    }
#pragma unroll
    for (int i = 0; i < 4; i++) {
      asm volatile("cvt.rn.bf16x2.f32 %0, %1, %2;\n" : "=r"(k0[hd][i]) : "f"(acc[33 + 16 * hd + 4 * i]), "f"(acc[32 + 16 * hd + 4 * i]));
    }
  }
}
__device__ __forceinline__ void attn_own(const uint32_t (&k0)[2][4], const uint32_t (&k1)[2][4], bool le0, bool le1,
                                         const uint32_t (&qa)[2][8], float (&l)[2][4]) {
#pragma unroll
  for (int hd = 0; hd < 2; hd++) {
    float s0[4], s1[4];
    mma16816_z(s0, qa[hd][0], qa[hd][1], qa[hd][2], qa[hd][3], k0[hd][0], k0[hd][1]);
    mma16816_z(s1, qa[hd][0], qa[hd][1], qa[hd][2], qa[hd][3], k1[hd][0], k1[hd][1]);
    mma16816(s0, qa[hd][4], qa[hd][5], qa[hd][6], qa[hd][7], k0[hd][2], k0[hd][3]);
    mma16816(s1, qa[hd][4], qa[hd][5], qa[hd][6], qa[hd][7], k1[hd][2], k1[hd][3]);
    l[hd][0] = s0[0];
    l[hd][1] = s0[1];
    l[hd][2] = le0 ? s1[2] : s0[2];
    l[hd][3] = le1 ? s1[3] : s0[3];
  }
}
template <int N> __device__ __forceinline__ void quad_softmax(float (&x)[N][2], uint32_t (&pp)[N]) {
  const float c2 = 1.4426950408889634f;
  uint32_t q[N], mx[N / 2];
#pragma unroll
  for (int n = 0; n < N; n++) {
    const uint32_t r = pack_bf16(x[n][0], x[n][1]);
    q[n] = bfma2(r, 0x3e353e35u, bmul2(r, 0x379e379eu));
    x[n][0] = bf_lo(q[n]);
    x[n][1] = bf_hi(q[n]);
  }
#pragma unroll
  for (int n = 0; n < N / 2; n++)
    mx[n] = bmax2(__byte_perm(q[2 * n], q[2 * n + 1], 0x5410), __byte_perm(q[2 * n], q[2 * n + 1], 0x7632));
#pragma unroll
  for (int o = 1; o <= 2; o++)
#pragma unroll
    for (int n = 0; n < N / 2; n++) mx[n] = bmax2(mx[n], __shfl_xor_sync(0xffffffffu, mx[n], o));
  float m[N], t[N];
#pragma unroll
  for (int n = 0; n < N / 2; n++) {
    m[2 * n] = bf_lo(mx[n]);
    m[2 * n + 1] = bf_hi(mx[n]);
  }
#pragma unroll
  for (int n = 0; n < N; n++) {
    const float nm = -m[n] * c2;
    x[n][0] = ex2(fmaf(x[n][0], c2, nm));
    x[n][1] = ex2(fmaf(x[n][1], c2, nm));
    t[n] = x[n][0] + x[n][1];
  }
#pragma unroll
  for (int o = 1; o <= 2; o++)
#pragma unroll
    for (int n = 0; n < N; n++) t[n] += __shfl_xor_sync(0xffffffffu, t[n], o);
#pragma unroll
  for (int n = 0; n < N; n++) {
    const float inv = rcp(t[n]);
    pp[n] = pack_bf16(x[n][0] * inv, x[n][1] * inv);
  }
}
__device__ __forceinline__ void attn_pv(uint32_t dst, const uint32_t (&va)[4], const uint32_t (&vb)[4], uint32_t pp,
                                        uint32_t maskLE) {
  const uint32_t b0 = pp & ~maskLE, b1 = pp & maskLE;
  float oa[4], ob[4];
  mma16816_z(oa, va[0], va[1], va[2], va[3], b0, b1);
  mma16816_z(ob, vb[0], vb[1], vb[2], vb[3], b0, b1);
  stsm4t(dst, pack_bf16(oa[0], oa[1]), pack_bf16(oa[2], oa[3]), pack_bf16(ob[0], ob[1]), pack_bf16(ob[2], ob[3]));
}

template <int MODE>
__global__ void __cluster_dims__(2, 1, 1) __launch_bounds__(NTHREADS, 1)
fused_kernel(const Params p, const __grid_constant__ CUtensorMap tmX, const __grid_constant__ CUtensorMap tmW,
             const __grid_constant__ CUtensorMap tmWo,
             const __grid_constant__ CUtensorMap tmQ,
             const __grid_constant__ CUtensorMap tmXh, const __grid_constant__ CUtensorMap tmWh) {
  extern __shared__ __align__(1024) uint8_t smem[];
  const uint32_t sb = smem_u32(smem);
  const uint32_t bars = sb + OFF_BAR;
  const int tid = threadIdx.x, lane = tid & 31, warp = __shfl_sync(0xffffffffu, tid >> 5, 0);
  const int rank = blockIdx.x & 1;
  const bool halo_cta = blockIdx.x < 4;
  if (halo_cta && MODE != 0) return;
  int grp, mem;
  {
    const int t = (blockIdx.x >> 1) - 4, u = t - 32;
    const int q7 = (u * 37) >> 8;
    const bool lo = (unsigned)t < 32u, mid = (unsigned)u < 28u;
    grp = lo ? (t & 7) : (mid ? 1 + u - 7 * q7 : 0);
    mem = lo ? (t >> 3) : (mid ? 4 + q7 : (t < 0 ? t + 6 : t - 54));
  }
  const int rg = (grp >> 2) * 4 + (mem >> 1), hp = (grp & 3) * 4 + (mem & 1) * 2 + rank;
  const int rb2 = (grp >> 2) * 8 + mem, cb2 = (grp & 3) * 2 + rank;
  const int chb = grp * 16 + mem * 2 + rank;
  const int cta = rg * 16 + hp;
  const int par = rg >> 2, gidx = rg & 3;

  if (tid < 256 && !halo_cta && MODE != 2) {
    const int r = tid >> 3, c = tid & 7;
    const uint32_t so = r * 128 + ((c ^ (r & 7)) << 4);
    const __nv_bfloat16* wg0 = p.w + (size_t)r * (3 * DM) + hp * 64 + c * 8;
    const __nv_bfloat16* xg0 = p.x + (size_t)(2 * (gidx * 256 + r) + par) * DM + c * 8;
#pragma unroll
    for (int j = 0; j < 3; j++) cp_async16n(sb + OFF_1B + j * 4096 + so, wg0 + j * DM);
#pragma unroll
    for (int i = 0; i < 8; i++) cp_async16n(sb + i * 4096 + so, xg0 + (size_t)i * 64 * DM);
    asm volatile("cp.async.commit_group;\n" ::: "memory");
  }
  if (tid == 256) {
    prefetch_tmap(halo_cta ? &tmXh : &tmX);
#pragma unroll
    for (int i = 0; i < NS1B; i++) mbar_init(bars + 8 * (BAR_FULLB + i), 1);
#pragma unroll
    for (int i = 0; i < NS1A; i++) mbar_init(bars + 8 * (BAR_FULLA + i), 1);
    asm volatile("fence.mbarrier_init.release.cluster;\n" ::: "memory");
    if (!halo_cta && MODE != 2) {
      mbar_expect_tx(bars + 8 * (BAR_FULLB + 1), STG1B);
      tma_load_3d(sb + OFF_1B + 1 * STG1B, &tmW, bars + 8 * (BAR_FULLB + 1), hp * 64, 32, 0);
      mbar_expect_tx(bars + 8 * (BAR_FULLB + 2), STG1B);
      tma_load_3d(sb + OFF_1B + 2 * STG1B, &tmW, bars + 8 * (BAR_FULLB + 2), hp * 64, 64, 0);
    } else {
      prefetch_tmap(&tmWh);
    }
  } else if (tid == 288) {
#pragma unroll
    for (int i = 0; i < NS1A; i++) mbar_init(bars + 8 * (BAR_EMPTYA + i), 4);
#pragma unroll
    for (int i = 0; i < NS1B; i++) mbar_init(bars + 8 * (BAR_EMPTYB + i), 2);
    asm volatile("fence.mbarrier_init.release.cluster;\n" ::: "memory");
  } else if (tid == 320) {
#pragma unroll
    for (int i = 0; i < NS2; i++) {
      mbar_init(bars + 8 * (BAR_FULL2 + i), 1);
      mbar_init(bars + 8 * (BAR_EMPTY2 + i), 4);
    }
    mbar_init(bars + 8 * BAR_DEAD, 2);
    mbar_init(bars + 8 * (BAR_DEAD + 1), 2);
    mbar_init(bars + 8 * BAR_X, 2);
    mbar_init(bars + 8 * BAR_REL, WAVE ? 1 : 2);
    asm volatile("fence.mbarrier_init.release.cluster;\n" ::: "memory");
  } else if (tid == 352) {
    mbar_init(bars + 8 * BAR_T, 1);
    mbar_init(bars + 8 * BAR_UH, 3);
    mbar_init(bars + 8 * BAR_LFREE, 4);
    mbar_init(bars + 8 * BAR_LAND, 1);
    mbar_init(bars + 8 * BAR_U, 1);
    mbar_init(bars + 8 * BAR_Q, 1);
    mbar_init(bars + 8 * BAR_STG, 9);
    asm volatile("fence.mbarrier_init.release.cluster;\n" ::: "memory");
  }
  if (warp == 8) PROF2(23);
  cluster_sync_all();
  if (warp == 8) PROF2(24);

  if (warp >= 8) {
    const int hw = warp - 8;
    const int lr = lane & 7, lm = lane >> 3;
    auto g1_issue_a = [&](int j, int s) {
      const uint32_t fb = bars + 8 * (BAR_FULLA + s);
      mbar_expect_tx(fb, STG1A);
      tma_load_3d_mc(sb + s * STG1A + rank * 16384, &tmX, fb, j * 64, par, gidx * 256 + rank * 128);
    };
    auto g1_issue_b = [&](int kb, int s) {
      const uint32_t fb = bars + 8 * (BAR_FULLB + s);
      mbar_expect_tx(fb, STG1B);
      tma_load_3d(sb + OFF_1B + s * STG1B, &tmW, fb, hp * 64, kb * 32, 0);
    };
    asm volatile("setmaxnreg.dec.sync.aligned.u32 %0;\n" :: "n"(REG_HELP));

    if (halo_cta) {
      if (hw == 0) {
        int s = 0, ph = 1;
#pragma unroll 1
        for (int kb = 0; kb < 16; kb++) {
          mbar_wait(bars + 8 * (BAR_EMPTYB + s), ph);
          const uint32_t fb = bars + 8 * (BAR_FULLB + s), st = sb + s * STGH;
          if (elect_one()) {
            mbar_expect_tx(fb, STGH);
            tma_load_4d(st, &tmXh, fb, kb * 64, 248, 0, 0);
            tma_load_3d(st + 8192, &tmWh, fb, 0, kb * 64, 16 + blockIdx.x * 4);
            tma_load_3d(st + 8192 + 32768, &tmWh, fb, 0, kb * 64, 32 + blockIdx.x * 4);
          }
          if (++s == 3) { s = 0; ph ^= 1; }
        }
      }
      __syncwarp();
    } else if (hw == 0) {
      uint32_t epoch = 0;
      if (lane < (MODE == 2 ? NS2 : 2)) mbar_arrive_cluster_n(mapa(bars, rank) + 8 * (BAR_EMPTY2 + lane), 4);
      if (MODE != 2) {
      epoch = ld_relaxed(g_flag_o + 2 * cta) + 1;
      if (lane == 0) {
        mbar_expect_tx(bars + 8 * BAR_U, 32768);
        mbar_expect_tx(bars + 8 * BAR_LAND, 32768);
        mbar_expect_tx(bars + 8 * BAR_Q, 32768);
        mbar_expect_tx(bars + 8 * BAR_T, T_END);
      }
      {
        int sa = 1, pha = 1, sbb = 2, phb = 1;
#pragma unroll 1
        for (int kb = 2; kb < 32; kb++) {
          if (!(kb & 1)) {
            mbar_wait(bars + 8 * (BAR_EMPTYA + sa), pha);
            if (elect_one()) g1_issue_a(kb >> 1, sa);
            if (++sa == NS1A) { sa = 0; pha ^= 1; }
          }
          mbar_wait(bars + 8 * (BAR_EMPTYB + sbb), phb);
          if (kb > 2 && elect_one()) g1_issue_b(kb, sbb);
          __syncwarp();
          if (kb >= PF0 && kb < PF0 + 12)
            prefetch_l2((kb < PF0 + 8 ? p.q + (size_t)chb * 16384 + (kb - PF0) * 2048 : p.wo + (size_t)chb * 8192 + (kb - PF0 - 8) * 2048) + lane * 64);
          if (kb == 4) PROF2(27);
          if (kb == 1) PROF2(38);
          if (kb == 2) PROF2(39);
          if (++sbb == NS1B) { sbb = 0; phb ^= 1; }
        }
      }
      static_assert(32 % NS1B == 2 && (32 / NS1B) % 2 == 0 && OFF_Q == OFF_1B && 2 * STG1B == 6 * 4096, "slots / parity of these loads");
      const uint8_t* tab = reinterpret_cast<const uint8_t*>(g_tab);
      if (lane == 0) {
        prefetch_tmap(&tmWo);
        prefetch_tmap(&tmQ);
        bulk_load(sb + OFF_T + T_A1, tab + T_A1, T_END - T_A1, bars + 8 * BAR_T);
        mbar_wait(bars + 8 * (BAR_EMPTYB + 2), 1);
        tma_load_5d(sb + OFF_Q + 6 * 4096, &tmQ, bars + 8 * BAR_Q, (chb & ~1) * 8, rank * 32 + 24);
        tma_load_5d(sb + OFF_Q + 7 * 4096, &tmQ, bars + 8 * BAR_Q, (chb & ~1) * 8, rank * 32 + 28);
        if (gidx != 0) wait_flag(g_flag_h + (hp >> 2), epoch);
      }
      __syncwarp();
      {
        uint4 hk0 = make_uint4(0, 0, 0, 0), hk1 = hk0, hv0 = hk0, hv1 = hk0;
        if (gidx != 0) {
          const uint4* src = g_halo + cta * 128 + lane;
          hk0 = __ldcg(src); hk1 = __ldcg(src + 32); hv0 = __ldcg(src + 64); hv1 = __ldcg(src + 96);
        }
        if (lane == 0) {
          mbar_wait(bars + 8 * (BAR_EMPTYB + 3), 1);
          bulk_load(sb + OFF_T, tab, T_TW, bars + 8 * BAR_T);
        }
        __syncwarp();
        PROF2(18);
        sts128(sb + OFF_L0 + 1024 + lane * 16, hk0.x, hk0.y, hk0.z, hk0.w);
        sts128(sb + OFF_L0 + 1536 + lane * 16, hk1.x, hk1.y, hk1.z, hk1.w);
        stsm4(sb + OFF_L0 + lr * 128 + ((lm ^ lr) << 4), hv0.x, hv0.y, hv0.z, hv0.w);
        stsm4(sb + OFF_L0 + lr * 128 + (((4 + lm) ^ lr) << 4), hv1.x, hv1.y, hv1.z, hv1.w);
        __syncwarp();
        if (lane == 0) {
          mbar_arrive(bars + 8 * BAR_STG);
          mbar_wait(bars + 8 * (BAR_EMPTYB + 4), 1);
          bulk_load(sb + OFF_T + T_TW, tab + T_TW, T_A1 - T_TW, bars + 8 * BAR_T);
          mbar_wait(bars + 8 * BAR_EMPTYB, 0);
#pragma unroll 1
          for (int i = 0; i < 6; i++) tma_load_5d(sb + OFF_Q + i * 4096, &tmQ, bars + 8 * BAR_Q, (chb & ~1) * 8, rank * 32 + i * 4);
        }
        __syncwarp();
      }
      }
      if (MODE != 1) {
        auto korder = [&](int i) { return MODE == 2 ? i : g2_k(hp, i); };
        if (MODE == 0) {
          mbar_wait_idle(bars + 8 * (BAR_EMPTY2 + 2), 0);
          if (elect_one()) {
            mbar_expect_tx(bars + 8 * BAR_FULL2, STG2);
            tma_load_3d(sb + g2_b(0), &tmWo, bars + 8 * BAR_FULL2, 0, korder(0) * 64, cb2 * 2);
            tma_load_3d(sb + g2_b(1), &tmWo, bars + 8 * (BAR_FULL2 + 1), 0, korder(1) * 64, cb2 * 2);
          }
        }
        PROF2(20);
        const __nv_bfloat16* osrc = g_o + (size_t)(rb2 >> 1) * 16 * 16384 + ((rb2 & 1) * 2 + rank) * 4096;
        const uint32_t* flag = g_flag_o + (rb2 >> 1) * 32 + korder(lane & 15) * 2 + (rb2 & 1);
        uint32_t ready = MODE == 0 ? 0u : ~0u, pv = 0;
#pragma unroll
        for (int i = MODE == 0 ? 2 : 0; i < 16; i++) {
          const int kb = korder(i), s = i % NS2, ph = (i / NS2) & 1;
          const uint32_t fb = bars + 8 * (BAR_FULL2 + s);
          if (!((ready >> i) & 1)) {
            int n = 0;
            do {
              ready |= __ballot_sync(0xffffffffu, ld_acquire(flag) == epoch);
            } while (!((ready >> i) & 1) && ++n < SPIN_LIMIT);
            fence_async_all();
          }
          if (i == 2) PROF(21);
          mbar_wait(bars + 8 * (BAR_EMPTY2 + s), ph);
          if (elect_one()) {
            mbar_expect_tx(fb, STG2);
            asm volatile(
                "cp.async.bulk.shared::cluster.global.mbarrier::complete_tx::bytes.multicast::cluster [%0], [%1], %2, [%3], %4;\n"
                ::"r"(sb + g2_a(s) + rank * 8192), "l"(osrc + kb * 16384), "r"(8192), "r"(fb), "h"((uint16_t)3) : "memory");
            if (MODE != 0 || i >= 4) tma_load_3d(sb + g2_b(s), &tmWo, fb, 0, kb * 64, cb2 * 2);
          }
          if (MODE == 0 && i == LA0) pv = ld_relaxed(flag);
          if (MODE == 0 && i == LA1) {
            ready |= __ballot_sync(0xffffffffu, pv == epoch);
            asm volatile("fence.acquire.gpu;\n" ::: "memory");
            fence_async_all();
          }
          if (i == 3) PROF(37);

        }
      }
      __syncwarp();
    } else if (MODE != 2) {
      {
        const int g = lane >> 2, t = lane & 3;
        uint32_t w[2][4];
#pragma unroll
        for (int h = 0; h < 2; h++) {
          const uint2 x = __ldg(reinterpret_cast<const uint2*>(p.shift_k + ((chb & ~1) * 8 + h * 8 + g) * 4));
          w[h][0] = __byte_perm(x.x, x.x, 0x1010);
          w[h][1] = __byte_perm(x.x, x.x, 0x3232);
          w[h][2] = __byte_perm(x.y, x.y, 0x1010);
          w[h][3] = __byte_perm(x.y, x.y, 0x3232);
        }
        auto swz = [](int r) { return (((r & 29) | ((r ^ (r >> 2)) & 2)) << 5) | (r & 16); };
        const uint32_t kring = sb + OFF_H + (hw - 1) * 8192, vring = kring + 4096;
        const int s0 = rank * 32 + (hw - 1) * 11, s1 = hw == 3 ? rank * 32 + 32 : s0 + 11;
        const size_t goff = (size_t)(lane >> 1) * DM + (chb & ~1) * 8 + (lane & 1) * 8;
        const __nv_bfloat16* kg = p.k + goff;
        const __nv_bfloat16* vg = p.v + goff;
        const uint32_t d0 = swz(lane >> 1) ^ ((lane & 1) << 4), d1 = swz(16 + (lane >> 1)) ^ ((lane & 1) << 4);
        auto issue = [&](int st) {
          const uint32_t so = (st & 3) << 10;
          cp_async16(kring + so + d0, kg + (size_t)st * 32 * DM, 16);
          cp_async16(kring + so + d1, kg + (size_t)(st * 32 + 16) * DM, 16);
          cp_async16(vring + so + d0, vg + (size_t)st * 32 * DM, 16);
          cp_async16(vring + so + d1, vg + (size_t)(st * 32 + 16) * DM, 16);
        };
        const int xa = 8 * (lr >> 1) + 2 * lm + (lr & 1), xb = 8 * (lr >> 1) - 4 + 2 * (lm & 1) + (lr & 1);
        const uint32_t la = swz(xa), lb = swz(xb & 31);
        const int backb = xb < 0 ? 1 : 0;
        const uint32_t ud[2] = {mapa(sb + OFF_U + g * 4096 + t * 16, 0), mapa(sb + OFF_U + g * 4096 + t * 16, 1)};
        const uint32_t ub[2] = {mapa(bars + 8 * BAR_U, 0), mapa(bars + 8 * BAR_U, 1)};
        if (lane == 0) mbar_wait(bars + 8 * (BAR_FULLB + NS1B - 1), 0);
        __syncwarp();
        if (lane >= 24) cp_async16(kring + (((s0 - 1) & 3) << 10) + d1, s0 > 0 ? kg + (size_t)(s0 * 32 - 16) * DM : kg, s0 > 0 ? 16 : 0);
        issue(s0);
        asm volatile("cp.async.commit_group;\n" ::: "memory");
        issue(s0 + 1);
        asm volatile("cp.async.commit_group;\n" ::: "memory");
#pragma unroll 1
        for (int st = s0; st < s1; st++) {
          if (st + 2 < s1) issue(st + 2);
          if (hw == 1 && st - s0 < 8) prefetch_l2(p.ssm_k + (size_t)(chb * 8 + st - s0) * SEQ + lane * 64);
          if (hw == 2 && st == s0 + 4 && lane < 2) prefetch_l2(g_tab + (chb * 2 + lane) * 32);
          const uint32_t uo = (st ^ ((g ^ (st >> 2)) & 1)) * 64;
          asm volatile("cp.async.commit_group;\n" ::: "memory");
          asm volatile("cp.async.wait_group 2;\n" ::: "memory");
          __syncwarp();
#pragma unroll
          for (int h = 0; h < 2; h++) {
            uint32_t e[6], vv[4], e4[4];
            ldsm4t(e4, kring + ((st & 3) << 10) + (la ^ (h << 4)));
            ldsm2t(e[0], e[1], kring + (((st - backb) & 3) << 10) + (lb ^ (h << 4)));
            ldsm4t(vv, vring + ((st & 3) << 10) + (la ^ (h << 4)));
            e[2] = e4[0]; e[3] = e4[1]; e[4] = e4[2]; e[5] = e4[3];
            uint32_t o[5];
#pragma unroll
            for (int i = 0; i < 5; i++) o[i] = __byte_perm(e[i], e[i + 1], 0x5432);
#pragma unroll
            for (int i = 0; i < 4; i++) {
              uint32_t a = bmul2(o[i], w[h][3]);
              a = bfma2(e[i + 1], w[h][2], a);
              a = bfma2(o[i + 1], w[h][1], a);
              a = bfma2(e[i + 2], w[h][0], a);
              vv[i] = bmul2(a, vv[i]);
            }
            st_async128(ud[h] + uo, ub[h], vv[0], vv[1], vv[2], vv[3]);
          }
          __syncwarp();
        }
        PROF(16);
      }
      {
        const int rw = (lane >> 3) + (lane & 4), ck = lane & 3;
        const uint32_t so = rw * 64 + ck * 16, dof = rw * 128 + ((ck ^ rw) << 4);
        const uint8_t* hsrc = reinterpret_cast<const uint8_t*>(p.ssm_k + (size_t)chb * 8 * SEQ) + so;
        const float dv = lane < 8 ? __bfloat162float(p.ssm_D[chb * 8 + lane]) : 0.f;
        uint32_t x[32];
        auto load = [&](const uint8_t* src, int i) {
          asm volatile("ld.v4.u32 {%0,%1,%2,%3}, [%4];\n" : "=r"(x[4 * i]), "=r"(x[4 * i + 1]), "=r"(x[4 * i + 2]), "=r"(x[4 * i + 3])
                       : "l"(src + i * 512) : "memory");
        };
#pragma unroll
        for (int i = 0; i < 8; i++) load(hsrc + (hw - 1) * 4096, i);
        nb_sync(NB_HELP3, 96);
        mbar_wait(bars + 8 * BAR_U, 0);
        int eh = 0;
#pragma unroll 1
        for (int n = 2 * (hw - 1); n < 16; n += (n & 1) ? 5 : 1) {
          const int c = n >> 1;
          const uint8_t* nsrc = (n & 1) ? hsrc + (c < 5 ? c + 3 : c) * 4096
                                        : smem + OFF_U + c * 4096 + (so ^ (((c ^ (lane >> 2)) & 1) << 6));
          const uint32_t dst = sb + ((n & 1) ? OFF_U : OFF_H) + c * 4096 + dof;
          const float dc = __shfl_sync(0xffffffffu, dv, c);
          const float h0 = bf_lo(x[0]) + ((lane | (n & 1)) == 0 ? dc : 0.f), h1 = bf_hi(x[0]);
          x[0] = pack_bf16(h0, h1);
          uint32_t m[2] = {x[0], x[1]};
#pragma unroll
          for (int i = 2; i < 32; i++) asm("max.xorsign.abs.bf16x2 %0, %0, %1;\n" : "+r"(m[i & 1]) : "r"(x[i]));
          asm("max.xorsign.abs.bf16x2 %0, %0, %1;\n" : "+r"(m[0]) : "r"(m[1]));
          const uint32_t e = max(__reduce_max_sync(0xffffffffu, max((m[0] >> 7) & 255u, (m[0] >> 23) & 255u)), 5u);
          const uint32_t sc = (259u - e) * 0x00800080u;
#pragma unroll
          for (int i = 0; i < 8; i++) {
            uint32_t o[4];
#pragma unroll
            for (int j = 0; j < 4; j++) {
              const uint32_t v = bmul2(x[4 * i + j], sc);
              asm("cvt.rn.f16x2.f32 %0, %1, %2;\n" : "=r"(o[j]) : "f"(bf_hi(v)), "f"(i + j == 0 ? h0 * bf_hi(sc) : bf_lo(v)));
            }
            sts128((dst + (i & 3) * 1024) ^ ((i >> 2) << 6), o[0], o[1], o[2], o[3]);
            load(nsrc, i);
          }
          if (n & 1) {
            const int f = min(max((int)e + eh - 129, 0), 254);
            if (lane == 0) asm volatile("st.shared.u32 [%0], %1;\n" ::"r"(sb + OFF_SC + c * 4), "r"(f << 23) : "memory");
          }
          eh = e;
        }
        fence_async_smem();
        __syncwarp();
        if (lane == 0) mbar_arrive(bars + 8 * BAR_UH);
        PROF(32);
      }
      if (hw < 3) {
        const uint32_t rb = mapa(bars, lane & 1);
        const uint32_t epoch = ld_relaxed(g_flag_o + 2 * cta + hw - 1) + 1;
        const bool own = hw - 1 == (rb2 & 1);
        nb_sync(NB_OREADY + hw - 1, 160);
        if (lane == 0) {
          asm volatile("cp.async.bulk.global.shared::cta.bulk_group [%0], [%1], %2;\n" ::"l"(g_o + (size_t)cta * 16384 + (hw - 1) * 8192),
                       "r"(sb + OFF_OP + (own ? 16384 : 0)), "r"(16384) : "memory");
          bulk_commit();
        }
        if (!WAVE && lane < 2) {
          mbar_arrive_cluster(rb + 8 * (BAR_EMPTY2 + 2));
          mbar_arrive_cluster(rb + 8 * (BAR_EMPTY2 + 3));
        }
        if (lane == 0) {
          bulk_wait0();
          if (own) mbar_expect_tx(bars + 8 * (BAR_FULL2 + 1), 16384);
          if (!WAVE || !own) mbar_arrive_cluster(mapa(bars, own ? rank : rank ^ 1) + 8 * BAR_X);
          st_release(g_flag_o + 2 * cta + hw - 1, epoch);
          if (!WAVE || !own) mbar_arrive(bars + 8 * BAR_REL);
        }
        __syncwarp();
        PROF(own ? 17 : 19);
      } else {
        mbar_wait_idle(bars + 8 * BAR_REL, 0);
        if (MODE == 0) {
          mbar_wait(bars + 8 * BAR_X, 0);
          if (elect_one())
            asm volatile("cp.async.bulk.shared::cluster.shared::cta.mbarrier::complete_tx::bytes [%0], [%1], %2, [%3];\n"
                         ::"r"(mapa(sb + OFF_OP, rank ^ 1)), "r"(sb + OFF_OP + 16384), "r"(16384),
                         "r"(mapa(bars + 8 * BAR_FULL2, rank ^ 1)) : "memory");
        }
        if (MODE == 0) {
          mbar_wait_idle(bars + 8 * BAR_DEAD, 0);
          if (elect_one()) {
            tma_load_3d(sb + g2_b(2), &tmWo, bars + 8 * (BAR_FULL2 + 2), 0, g2_k(hp, 2) * 64, cb2 * 2);
            tma_load_3d(sb + g2_b(3), &tmWo, bars + 8 * (BAR_FULL2 + 3), 0, g2_k(hp, 3) * 64, cb2 * 2);
          }
        }
        __syncwarp();
      }
      {
        const int c8 = (4 * (lr >> 1) + 2 * (lm & 1) + (lr & 1)) & 7;
        const bool own = (lr >> 2) == rank;
        const uint32_t ya = sb + (own ? y_slot(c8 & 1, c8 >> 1) : OFF_LAND + c8 * 2048);
        const uint32_t yx = ((lm >> 1) ^ lr) << 4;
        const int row = (lane >> 3) * 8 + ((lane >> 2) & 1);
        uint2* og = reinterpret_cast<uint2*>(p.out + (size_t)(rank * 1024 + row) * (2 * DM) + (chb & ~1) * 8 + (lane & 3) * 4);
        const uint32_t qa = sb + OFF_Q + lane * 8;
        mbar_wait(bars + 8 * BAR_Q, 0);
        mbar_wait_idle(bars + 8 * BAR_LAND, 0);
        PROF(33);
        const uint32_t t0 = clock();
#pragma unroll 1
        for (int j = hw - 1; j < 16; j += 3) {
          uint32_t y[4][4];
          uint2 q[8];
          while ((uint32_t)clock() - t0 < j * PACE) __nanosleep(40);
          const uint32_t qj = qa + j * 2048;
#pragma unroll
          for (int i = 0; i < 4; i++) ldsm4t(y[i], ya + j * 128 + (yx ^ (i << 5)));
#pragma unroll
          for (int i = 0; i < 8; i++) q[i] = lds64(qj + i * 256);
#pragma unroll
          for (int i = 0; i < 8; i++) {
            og[(size_t)(j * 64 + (i >> 2) * 32 + (i & 3) * 2) * (2 * DM / 4)] =
                make_uint2(bmul2(q[i].x, y[i >> 1][2 * (i & 1)]), bmul2(q[i].y, y[i >> 1][2 * (i & 1) + 1]));
            if (i < 7) asm volatile("nanosleep.u32 %0;\n" ::"r"(FINE) : "memory");
          }
        }
      }
      PROF(22);
    }
    cluster_sync_all();
  } else {
    asm volatile("setmaxnreg.inc.sync.aligned.u32 %0;\n" :: "n"(REG_MATH));
    if (warp == 0) PROF2(26);
    const int wg = warp >> 2;
    const int wtid = tid & 127;
    const bool signaller = (wtid == 0) || (wtid == 32);
    const uint32_t rbars = mapa(bars, wtid >> 5 & 1);

    if (halo_cta) {
      const uint32_t epoch = ld_relaxed(g_flag_h + blockIdx.x) + 1;
      float acc0[64], acc1[64];
      int s = 0, ph = 0;
#pragma unroll 1
      for (int kb = 0; kb < 16; kb++) {
        mbar_wait(bars + 8 * (BAR_FULLB + s), ph);
        const uint32_t st = sb + s * STGH;
        const uint64_t da = mkdesc(st, 16, 1024, 1);
        const uint64_t db = mkdesc(st + 8192 + wg * 32768, 8192, 1024, 1);
        wg_fence();
#pragma unroll
        for (int kk = 0; kk < 4; kk++) {
          wgmma_n128(acc0, da + 2 * kk, db + 128 * kk, kb + kk);
          wgmma_n128(acc1, da + 2 * kk, db + 1024 + 128 * kk, kb + kk);
        }
        wg_commit();
        wg_wait<0>();
        if (wtid == 0) mbar_arrive(bars + 8 * (BAR_EMPTYB + s));
        if (++s == 3) { s = 0; ph ^= 1; }
      }
      fence_regs(acc0);
      fence_regs(acc1);
      if ((warp & 3) != 3) {
#pragma unroll
        for (int hh = 0; hh < 2; hh++) {
          uint4* dst = g_halo + ((hh * 4 + (warp & 3) + 1) * 16 + blockIdx.x * 4) * 128 + wg * 64 + lane;
#pragma unroll
          for (int j = 0; j < 4; j++) {
            const int o = 16 * j + 2 * hh;
            dst[(j >> 1) * 128 + (j & 1) * 32] =
                make_uint4(pack_bf16(acc0[o], acc0[o + 1]), pack_bf16(acc0[o + 4], acc0[o + 5]),
                           pack_bf16(acc0[o + 8], acc0[o + 9]), pack_bf16(acc0[o + 12], acc0[o + 13]));
            dst[(2 + (j >> 1)) * 128 + (j & 1) * 32] =
                make_uint4(pack_bf16(acc1[o], acc1[o + 1]), pack_bf16(acc1[o + 4], acc1[o + 5]),
                           pack_bf16(acc1[o + 8], acc1[o + 9]), pack_bf16(acc1[o + 12], acc1[o + 13]));
          }
        }
      }
      nb_sync(NB_G1DONE, 256);
      if (tid == 0) st_release(g_flag_h + blockIdx.x, epoch);
      PROF(36);
      cluster_sync_all();
      return;
    }

    float acc[64];
    auto g2_step = [&](int s, int kb) {
      const uint64_t da = mkdesc(sb + g2_a(s) + wg * 8192, 16, 1024, 1);
      const uint64_t db = mkdesc(sb + g2_b(s), 8192, 1024, 1);
      wg_fence();
      wgmma_n128(acc, da, db, kb);
      wgmma_n128(acc, da + 2, db + 128, 1);
      wgmma_n128(acc, da + 4, db + 256, 1);
      wgmma_n128(acc, da + 6, db + 384, 1);
      wg_commit();
    };

    if (MODE != 2) {
    uint32_t a1[2][4], tw[16], d1[32];
    const uint32_t tb = sb + OFF_T + wtid * 16;
    const uint64_t dx = mkdesc(sb + OFF_U + wg * 4096, OFF_H - OFF_U, 1024, 1);
    auto s1 = [&](int it) {
      hmma_n128t<0>(d1, a1[0], dx + it * 512);
      hmma_n128t<1>(d1, a1[1], dx + it * 512 + 128);
      wg_commit();
    };
    auto ldtw = [&](int i) {
      const uint4 v = lds128(tb + T_TW + i * 2048);
      tw[4 * i] = v.x; tw[4 * i + 1] = v.y; tw[4 * i + 2] = v.z; tw[4 * i + 3] = v.w;
    };
    {
      float acc0[96], acc1[96];
      int sa = 0, pha = 0, sbb = 0, phb = 0;
      asm volatile("cp.async.wait_group 0;\n" ::: "memory");
      fence_async_smem();
      nb_sync(NB_FIRST, 256);
      if (tid == 0) {
        mbar_arrive(bars + 8 * BAR_FULLA);
        mbar_arrive(bars + 8 * BAR_FULLB);
      }
      PROF(0 + wg);
#pragma unroll 1
      for (int kb = 0; kb < 30; kb++) {
        if (!(kb & 1)) mbar_wait(bars + 8 * (BAR_FULLA + sa), pha);
        mbar_wait(bars + 8 * (BAR_FULLB + sbb), phb);
        if (kb == 0) PROF2(0 + wg);
        if (kb == 4 && wg == 0) PROF2(28);
        if (kb == 8 && wg == 0) PROF2(29);
        if (kb == 16 && wg == 0) PROF2(30);
        const uint64_t da = mkdesc(sb + sa * STG1A + wg * 16384 + (kb & 1) * 64, 16, 1024, 1);
        const uint64_t db = mkdesc(sb + OFF_1B + sbb * STG1B, 4096, 1024, 1);
        wg_fence();
        wgmma_n192(acc0, da, db, kb);
        wgmma_n192(acc1, da + 512, db, kb);
        wgmma_n192(acc0, da + 2, db + 128, 1);
        wgmma_n192(acc1, da + 514, db + 128, 1);
        wg_commit();
        wg_wait<1>();
        if (kb > 0) {
          if (wtid == 64) mbar_arrive(bars + 8 * (BAR_EMPTYB + (sbb == 0 ? NS1B - 1 : sbb - 1)));
          if (!(kb & 1) && signaller) mbar_arrive_cluster(rbars + 8 * (BAR_EMPTYA + (sa == 0 ? NS1A - 1 : sa - 1)));
        }
        if (++sbb == NS1B) { sbb = 0; phb ^= 1; }
        if ((kb & 1) && ++sa == NS1A) { sa = 0; pha ^= 1; }
      }
      const int blk0 = wg * 8 + (warp & 3);
      const int lr = lane & 7, lm = lane >> 3;
      const bool le0 = 2 * (lane & 3) <= (lane >> 2), le1 = 2 * (lane & 3) + 1 <= (lane >> 2);
      const uint32_t maskLE = (le0 ? 0x0000FFFFu : 0u) | (le1 ? 0xFFFF0000u : 0u);
      uint32_t k0[2][2][4], k1[2][2][4], qa[2][2][8];
      float l[2][2][4];
      {
        static_assert(15 % NS1A == 0 && 30 % NS1B == 0, "slots of the last k blocks");
        mbar_wait(bars + 8 * BAR_FULLA, 1);
        mbar_wait(bars + 8 * BAR_FULLB, 0);
        mbar_wait(bars + 8 * (BAR_FULLB + 1), 0);
        const uint64_t da = mkdesc(sb + wg * 16384, 16, 1024, 1);
        const uint64_t db = mkdesc(sb + OFF_1B, 4096, 1024, 1);
        wg_fence();
#pragma unroll
        for (int i = 0; i < 4; i++) wgmma_n192(acc0, da + 2 * i, db + (i >> 1) * (STG1B >> 4) + (i & 1) * 128, 1);
        wg_commit();
        wg_wait<1>();
        if (wtid == 64) mbar_arrive(bars + 8 * (BAR_EMPTYB + NS1B - 1));
#pragma unroll
        for (int i = 0; i < 2; i++) wgmma_n192(acc1, da + 512 + 2 * i, db + (i >> 1) * (STG1B >> 4) + (i & 1) * 128, 1);
        wg_commit();
        wg_wait<1>();
        fence_regs(acc0);
        attn_stage(sb, blk0, lane, acc0, k1[0]);
#pragma unroll
        for (int i = 2; i < 4; i++) wgmma_n192(acc1, da + 512 + 2 * i, db + (i >> 1) * (STG1B >> 4) + (i & 1) * 128, 1);
        wg_commit();
        attn_pack(acc0, qa[0], k0[0]);
        wg_wait<0>();
        fence_regs(acc1);
      }
      if (wtid == 64) mbar_arrive(bars + 8 * BAR_EMPTYB);
      PROF(2 + wg);
      attn_stage(sb, blk0 + 4, lane, acc1, k1[1]);
      __syncwarp();
      if (lane == 0) mbar_arrive(bars + 8 * BAR_STG);
      mbar_wait(bars + 8 * BAR_U, 0);
      attn_pack(acc1, qa[1], k0[1]);
      attn_own(k0[0], k1[0], le0, le1, qa[0], l[0]);
      attn_own(k0[1], k1[1], le0, le1, qa[1], l[1]);
      const uint32_t cho[2] = {(uint32_t)(((lm & 1) ^ lr) << 4), (uint32_t)(((2 + (lm & 1)) ^ lr) << 4)};
      const uint32_t obase = sb + OFF_OP + (wg == (rb2 & 1) ? 16384 : 0) + ((warp & 3) * 16 + lr) * 128;
      mbar_wait(bars + 8 * BAR_STG, 0);
      {
        uint32_t km[4][4], va[8][4], vb[8][4], pp[8];
        float x[8][2];
#pragma unroll
        for (int n = 0; n < 4; n++) {
          const int blk = blk0 + 4 * (n >> 1);
          to_arr(km[n], lds128(sb + (blk == 0 ? OFF_L0 + 1024 : OFF_KH + (blk - 1) * 2048) + (n & 1) * 512 + lane * 16));
        }
#pragma unroll
        for (int n = 0; n < 8; n++) {
          const int vr = (blk0 + 4 * ((n >> 1) & 1)) * 16 - 8 + 8 * (n >> 2) + 8 * (lm >> 1);
          const uint32_t vrow = sb + (vr < 0 ? OFF_L0 : OFF_VP + vr * 128) + lr * 128;
          ldsm4t(va[n], vrow + (cho[0] ^ ((n & 1) << 6)));
          ldsm4t(vb[n], vrow + (cho[1] ^ ((n & 1) << 6)));
        }
        const bool first = blk0 == 0 && gidx == 0;
#pragma unroll
        for (int n = 0; n < 4; n++) {
          const uint32_t(&q)[8] = qa[n >> 1][n & 1];
          float sm[4];
          mma16816_z(sm, q[0], q[1], q[2], q[3], km[n][0], km[n][1]);
          mma16816(sm, q[4], q[5], q[6], q[7], km[n][2], km[n][3]);
          if (n < 2 && first) sm[0] = sm[1] = -1e9f / 0.17677669529663687f;
          x[n][0] = le0 ? l[n >> 1][n & 1][0] : sm[0];
          x[n][1] = le1 ? l[n >> 1][n & 1][1] : sm[1];
          x[4 + n][0] = l[n >> 1][n & 1][2];
          x[4 + n][1] = l[n >> 1][n & 1][3];
        }
        quad_softmax<8>(x, pp);
#pragma unroll
        for (int n = 7; n >= 0; n--)
          attn_pv(obase + ((n >> 1) & 1) * 8192 + (n >> 2) * 1024 + (((4 * (n & 1) + lm) ^ lr) << 4), va[n], vb[n], pp[n],
                  maskLE);
      }
      fence_async_smem();
      nb_arrive(NB_OREADY + wg, 160);
    }

    {
      const int w = warp & 3;
      uint32_t a4[8][4];
      float d4[16];
      PROF(34 + wg);
      const uint64_t dz = mkdesc(sb + OFF_U + wg * 4096, 512, 128, 0);
      const uint64_t db2 = mkdesc(sb + OFF_T + T_B2, 128, 256, 0);
      mbar_wait(bars + 8 * BAR_T, 0);
      mbar_wait(bars + 8 * BAR_UH, 0);
      to_arr(a1[0], lds128(tb + T_A1));
      to_arr(a1[1], lds128(tb + T_A1 + 2048));
      wg_fence();
      s1(0);
      ldtw(0);
      ldtw(1);
      const uint32_t za = sb + (w < 2 ? OFF_U : OFF_H) + wg * 4096 + (w & 1) * 2048 + lane * 16;
      const uint32_t yl = (wtid ^ (4 * rank + wg)) * 16;
      const uint32_t yown = mapa(sb, rank) + yl, yrem = mapa(sb + OFF_LAND + wg * 2048, rank ^ 1) + yl;
      const uint32_t yb[2] = {mapa(bars + 8 * BAR_LAND, 0), mapa(bars + 8 * BAR_LAND, 1)};
      wg_wait<0>();
      fence_regs(d1);
      nb_sync(NB_WG + wg, 128);
      auto s4 = [&](int it) {
        wg_fence();
#pragma unroll
        for (int ks = 0; ks < 8; ks++) {
          const uint64_t d = dz + (it & 1) * 512 + (ks & 3) * 64 + (ks >> 2) * ((OFF_H - OFF_U) >> 4);
          if (ks == 0) fmma_n32t<0>(d4, a4[ks], d);
          else fmma_n32t<1>(d4, a4[ks], d);
        }
        wg_commit();
      };
      auto e4 = [&](int it) {
        fence_regs(d4);
        const float sc = __uint_as_float(lds32(sb + OFF_SC + wg * 4 + it * 8));
        uint32_t r[8];
#pragma unroll
        for (int i = 0; i < 8; i++) r[i] = pack_bf16(d4[2 * i] * sc, d4[2 * i + 1] * sc);
        const uint32_t o = (yown + y_slot(wg, it)) ^ ((it >> 1) << 5), m = (yrem + it * 4096) ^ ((it >> 1) << 5);
        if (it == 0) mbar_wait(bars + 8 * BAR_LFREE, 0);
        if (it == 3) mbar_wait(bars + 8 * (BAR_DEAD + 1), 0);
        st_async128(rank ? m : o, yb[0], r[0], r[2], r[1], r[3]);
        st_async128(rank ? o : m, yb[1], r[4], r[6], r[5], r[7]);
      };
      uint32_t a2[2][2][2][4], a3[2][2][4], d2[2][2][8], d3[2][8];
      auto s2a = [&]() {
        wg_fence();
#pragma unroll
        for (int c = 0; c < 4; c++) hmma_n32<0, 0>(d2[c & 1][c >> 1], a2[0][c & 1][c >> 1], db2 + (c >> 1) * 128);
      };
      auto s2b = [&]() {
        wg_fence();
#pragma unroll
        for (int c = 0; c < 4; c++) {
          hmma_n32<1, 0>(d2[c & 1][c >> 1], a2[1][c & 1][c >> 1], db2 + (c >> 1) * 128 + 64);
          if (c & 1) wg_commit();
        }
      };
      auto done = [&](int it) {
        if (it == 0) {
          if (signaller) mbar_arrive_cluster(rbars + 8 * BAR_LFREE);
        } else if (it >= 2 && wtid == 64) {
          mbar_arrive(bars + 8 * (BAR_DEAD + it - 2));
        }
        if (w == 0) PROF3(40 + 4 * wg + it);
      };
      fft_e1<0>(d1, tw, a2[0]);
      s2a();
      fft_e1<1>(d1, tw, a2[1]);
      s2b();
      s1(1);
      ldtw(2);
      ldtw(3);
#pragma unroll
      for (int i = 0; i < 8; i++) to_arr(a4[i], lds128(tb + T_A4 + i * 2048));
#pragma unroll
      for (int it = 0; it < 4; it++) {
        if (it == 0 || it == 3) wg_wait<2>(); else wg_wait<3>();
        fence_regs(d2[0][0]);
        fence_regs(d2[1][0]);
        fft_e2<0, 0>(d2[0][0], d2[1][0], a3[0]);
        fft_e2<0, 1>(d2[0][0], d2[1][0], a3[1]);
        if (it == 0 || it == 3) wg_wait<1>(); else wg_wait<2>();
        fence_regs(d2[0][1]);
        fence_regs(d2[1][1]);
        fft_e2<1, 0>(d2[0][1], d2[1][1], a3[0]);
        fft_e2<1, 1>(d2[0][1], d2[1][1], a3[1]);
        wg_fence();
        hmma_n32<0, 0>(d3[0], a3[0][0], db2);
        hmma_n32<0, 0>(d3[1], a3[0][1], db2);
        hmma_n32<1, 0>(d3[0], a3[1][0], db2 + 64);
        hmma_n32<1, 0>(d3[1], a3[1][1], db2 + 64);
        wg_commit();
        wg_wait<1>();
        if (it > 0) e4(it - 1);
        if (it < 3) {
          fence_regs(d1);
          fft_e1<0>(d1, tw, a2[0]);
        }
        wg_wait<0>();
        fence_regs(d3[0]);
        fence_regs(d3[1]);
        if (it < 3) s2a();
        fft_e3(d3, tw, za + (it & 1) * 8192);
        if (it < 3) {
          fft_e1<1>(d1, tw, a2[1]);
          s2b();
        }
        fence_async_smem();
        nb_sync(NB_WG + wg, 128);
        done(it);
        s4(it);
        if (it < 2) s1(it + 2);
      }
      if (PEEL && MODE == 0) {
        mbar_wait(bars + 8 * BAR_FULL2, 0);
        g2_step(0, 0);
        wg_wait<1>();
      } else {
        wg_wait<0>();
      }
      if (signaller) mbar_arrive_cluster(rbars + 8 * (BAR_EMPTY2 + 4));
      e4(3);
      if (PEEL && MODE == 0) {
        wg_wait<0>();
        if (signaller) mbar_arrive_cluster(rbars + 8 * BAR_EMPTY2);
      }
      PROF(6 + wg);
    }
    }

    if (MODE != 1) {
      int s = PEEL && MODE == 0, ph = 0;
#pragma unroll 1
      for (int kb = s; kb < STAG; kb++) {
        mbar_wait(bars + 8 * (BAR_FULL2 + s), ph);
        if (kb == 1) PROF(8 + wg);
        if (warp == 4) PROF2(40 + kb);
        g2_step(s, kb);
        wg_wait<0>();
        if (kb < 16 - NS2 && signaller) mbar_arrive_cluster(rbars + 8 * (BAR_EMPTY2 + s));
        if (++s == NS2) { s = 0; ph ^= 1; }
      }
      if (STAG < 16) {
        if (wg == LAST) nb_sync(NB_LEAD, 256);
#pragma unroll
        for (int kb = STAG; kb < 16; kb++) {
          mbar_wait(bars + 8 * (BAR_FULL2 + kb % NS2), (kb / NS2) & 1);
          g2_step(kb % NS2, 1);
        }
        if (wg != LAST) nb_arrive(NB_LEAD, 256);
      }
      wg_wait<0>();
      fence_regs(acc);
      PROF(10 + wg);
      const int lr = lane & 7, lm = lane >> 3;
      const uint32_t wbase = sb + warp * 2048;
      const uint32_t base = wbase + (lr + 8 * (lm & 1)) * 128;
#pragma unroll
      for (int j = 0; j < 16; j += 2) {
        const uint32_t a = base + (j >> 3) * 16384 + ((((j & 7) + (lm >> 1)) ^ lr) << 4);
        stsm4(a, pack_bf16(acc[4 * j], acc[4 * j + 1]), pack_bf16(acc[4 * j + 2], acc[4 * j + 3]),
              pack_bf16(acc[4 * j + 4], acc[4 * j + 5]), pack_bf16(acc[4 * j + 6], acc[4 * j + 7]));
      }
      __syncwarp();
      {
        const int rr = lane >> 4, ck = lane & 7, hf = (lane >> 3) & 1;
        uint4* og = reinterpret_cast<uint4*>(p.out + (size_t)(2 * ((rb2 & 7) * 128 + warp * 16 + rr) + (rb2 >> 3)) * (2 * DM) + DM + cb2 * 128 + hf * 64 + ck * 8);
        uint4 v[8];
#pragma unroll
        for (int i = 0; i < 8; i++) v[i] = lds128(wbase + hf * 16384 + (2 * i + rr) * 128 + ((ck ^ ((2 * i + rr) & 7)) << 4));
#pragma unroll
        for (int i = 0; i < 8; i++) og[(size_t)i * 4 * (2 * DM / 8)] = v[i];
      }
      PROF(12 + wg);
    }
    cluster_sync_all();
  }
}

typedef CUresult (*EncodeFn)(CUtensorMap*, CUtensorMapDataType, cuuint32_t, void*, const cuuint64_t*, const cuuint64_t*,
                             const cuuint32_t*, const cuuint32_t*, CUtensorMapInterleave, CUtensorMapSwizzle,
                             CUtensorMapL2promotion, CUtensorMapFloatOOBfill);

void make_map(EncodeFn enc, CUtensorMap* tm, const void* base, int rank, const cuuint64_t* dims, const cuuint64_t* strides,
              const cuuint32_t* box, CUtensorMapSwizzle swz) {
  cuuint32_t es[5] = {1, 1, 1, 1, 1};
  enc(tm, CU_TENSOR_MAP_DATA_TYPE_BFLOAT16, rank, const_cast<void*>(base), dims, strides, box, es,
      CU_TENSOR_MAP_INTERLEAVE_NONE, swz, CU_TENSOR_MAP_L2_PROMOTION_L2_256B, CU_TENSOR_MAP_FLOAT_OOB_FILL_NONE);
}

}

extern "C" void kernel_launch(void* const* d_in, const int* in_sizes, int n_in, void* d_out, int out_size) {
  static EncodeFn enc = nullptr;
  static bool coresident = true;
  if (!enc) {
    void* fn = nullptr;
    cudaDriverEntryPointQueryResult qr;
    cudaGetDriverEntryPoint("cuTensorMapEncodeTiled", &fn, cudaEnableDefault, &qr);
    enc = (EncodeFn)fn;
    cudaFuncSetAttribute(fused_kernel<0>, cudaFuncAttributeMaxDynamicSharedMemorySize, SMEM_BYTES);
    cudaFuncSetAttribute(fused_kernel<1>, cudaFuncAttributeMaxDynamicSharedMemorySize, SMEM_BYTES);
    cudaFuncSetAttribute(fused_kernel<2>, cudaFuncAttributeMaxDynamicSharedMemorySize, SMEM_BYTES);
    cudaLaunchConfig_t cfg = {};
    cfg.gridDim = dim3(NCTA);
    cfg.blockDim = dim3(NTHREADS);
    cfg.dynamicSmemBytes = SMEM_BYTES;
    cudaLaunchAttribute at;
    at.id = cudaLaunchAttributeClusterDimension;
    at.val.clusterDim.x = 2;
    at.val.clusterDim.y = 1;
    at.val.clusterDim.z = 1;
    cfg.attrs = &at;
    cfg.numAttrs = 1;
    int nclusters = 0;
    if (cudaOccupancyMaxActiveClusters(&nclusters, fused_kernel<0>, &cfg) == cudaSuccess) coresident = nclusters >= NCTA / 2;
    (void)cudaGetLastError();
  }
  CUtensorMap tmX, tmW, tmWo, tmQ, tmXh, tmWh;
  {
    cuuint64_t dims[3] = {1024, 2, 1024};
    cuuint64_t str[2] = {2048, 4096};
    cuuint32_t box[3] = {64, 1, 128};
    make_map(enc, &tmX, d_in[6], 3, dims, str, box, CU_TENSOR_MAP_SWIZZLE_128B);
  }
  {
    cuuint64_t dims[3] = {1024, 1024, 3};
    cuuint64_t str[2] = {6144, 2048};
    cuuint32_t box[3] = {64, 32, 3};
    make_map(enc, &tmW, d_in[7], 3, dims, str, box, CU_TENSOR_MAP_SWIZZLE_128B);
  }
  {
    cuuint64_t dims[3] = {64, 1024, 16};
    cuuint64_t str[2] = {2048, 128};
    cuuint32_t box[3] = {64, 64, 2};
    make_map(enc, &tmWo, d_in[8], 3, dims, str, box, CU_TENSOR_MAP_SWIZZLE_128B);
  }
  {
    cuuint64_t dims[5] = {1024, 2, 4, 4, 64};
    cuuint64_t str[4] = {2048, 8 * 2048, 2 * 2048, 32 * 2048};
    cuuint32_t box[5] = {16, 2, 4, 4, 4};
    make_map(enc, &tmQ, d_in[0], 5, dims, str, box, CU_TENSOR_MAP_SWIZZLE_NONE);
  }
  {
    cuuint64_t dims[4] = {1024, 256, 2, 4};
    cuuint64_t str[3] = {4096, 2048, 256 * 4096};
    cuuint32_t box[4] = {64, 8, 2, 4};
    make_map(enc, &tmXh, d_in[6], 4, dims, str, box, CU_TENSOR_MAP_SWIZZLE_128B);
  }
  {
    cuuint64_t dims[3] = {64, 1024, 48};
    cuuint64_t str[2] = {6144, 128};
    cuuint32_t box[3] = {64, 64, 4};
    make_map(enc, &tmWh, d_in[7], 3, dims, str, box, CU_TENSOR_MAP_SWIZZLE_128B);
  }
  Params p;
  p.q = (const __nv_bfloat16*)d_in[0];
  p.k = (const __nv_bfloat16*)d_in[1];
  p.v = (const __nv_bfloat16*)d_in[2];
  p.shift_k = (const __nv_bfloat16*)d_in[3];
  p.ssm_k = (const __nv_bfloat16*)d_in[4];
  p.ssm_D = (const __nv_bfloat16*)d_in[5];
  p.x = (const __nv_bfloat16*)d_in[6];
  p.w = (const __nv_bfloat16*)d_in[7];
  p.wo = (const __nv_bfloat16*)d_in[8];
  p.out = (__nv_bfloat16*)d_out;
  if (coresident) {
    fused_kernel<0><<<NCTA, NTHREADS, SMEM_BYTES>>>(p, tmX, tmW, tmWo, tmQ, tmXh, tmWh);
  } else {
    fused_kernel<0><<<4, NTHREADS, SMEM_BYTES>>>(p, tmX, tmW, tmWo, tmQ, tmXh, tmWh);
    fused_kernel<1><<<NCTA, NTHREADS, SMEM_BYTES>>>(p, tmX, tmW, tmWo, tmQ, tmXh, tmWh);
    fused_kernel<2><<<NCTA, NTHREADS, SMEM_BYTES>>>(p, tmX, tmW, tmWo, tmQ, tmXh, tmWh);
  }
}
```

```cpp
#include <cuda_runtime.h>
#include <cuda.h>
#include <cuda_bf16.h>
#include <stdint.h>

namespace {

constexpr int SEQ = 2048;
constexpr int DM = 1024;
constexpr int NCTA = 132;
constexpr int NTHREADS = 384;

constexpr int STG1A = 32768;
constexpr int NS1A = 3;
constexpr int STG1B = 12288;
constexpr int NS1B = 5;
constexpr int OFF_1B = NS1A * STG1A;
constexpr int STG2 = 32768;
constexpr int NS2 = 5;
constexpr int STGH = 73728;
constexpr int OFF_VP = 0;
constexpr int OFF_KH = 1 * STG2;
constexpr int OFF_OP = 2 * STG2;
constexpr int OFF_Q = 3 * STG2;
constexpr int T_A4 = 0, T_TW = 16384, T_B2 = 24576, T_A1 = 28672, T_END = 32768;
constexpr int OFF_U = 163840;
constexpr int OFF_H = OFF_U + 32768;
constexpr int OFF_T = OFF_U - T_END;
constexpr int OFF_LAND = 4 * STG2;
constexpr int OFF_BAR = OFF_H + 32768;
constexpr int OFF_SC = OFF_BAR + 512;
constexpr int OFF_L0 = OFF_BAR + 1024;
constexpr int SMEM_BYTES = OFF_L0 + 2048;
static_assert(OFF_T + T_A1 == OFF_1B + NS1B * STG1B && OFF_T + T_TW == OFF_1B + 4 * STG1B && OFF_LAND == OFF_T + T_A4, "layout");
static_assert(3 * STGH <= OFF_BAR && SMEM_BYTES <= 232448, "smem");

constexpr int BAR_FULLA = 0;
constexpr int BAR_EMPTYA = 3;
constexpr int BAR_FULLB = 6;
constexpr int BAR_EMPTYB = 11;
constexpr int BAR_FULL2 = 16;
constexpr int BAR_EMPTY2 = 21;
constexpr int BAR_T = 26;
constexpr int BAR_UH = 27;
constexpr int BAR_LFREE = 28;
constexpr int BAR_LAND = 29;
constexpr int BAR_U = 30;
constexpr int BAR_Q = 31;
constexpr int BAR_STG = 32;
constexpr int BAR_DEAD = 33;
constexpr int BAR_X = 35;
constexpr int BAR_REL = 36;

constexpr int NB_G1DONE = 1;
constexpr int NB_OREADY = 2;
constexpr int NB_WG = 4;
constexpr int NB_HELP3 = 6;
constexpr int NB_FIRST = 7;
constexpr int NB_LEAD = 8;

#define PACE 390u
#define PF0 20
#define EARLYS1 0
#define PEEL 1
#define IDLEW 1
#define WAVE 0
#define LA0 3
#define LA1 4
#define STAG 12
#define LAST 0
#define FINE 40
#define SCHED 1
#define REG_MATH 224
#define REG_HELP 56
constexpr int SPIN_LIMIT = 1 << 20;

__device__ __align__(1024) __nv_bfloat16 g_o[SEQ * DM];
__device__ uint32_t g_flag_o[256];
__device__ uint32_t g_flag_h[4];
__device__ uint4 g_halo[128 * 128];
__device__ __align__(128) const uint32_t g_tab[T_END / 4] = {
0x3c003c00,0x3bf13bff,0,0xafd6a648,0x3c003c00,0x3b993bce,0,0xb505b303,0x3c003c00,0x3af63b50,0,0xb7e3b67c,
0x3c003c00,0x3a0f3a8a,0,0xb93ab89b,0x3bc33bfe,0x3b773bfa,0xb3c6aa48,0xb5c2acb5,0x3a6d3b3b,0x389b3a4f,0xb8c4b6d7,0xba8ab8ec,
0x381d395f,0x26483505,0xbaddb9ed,0xbbffbb99,0x30b23564,0xb848b444,0xbbeabb88,0xbac2bbb6,0x3b0e3bf6,0x3a8a3bf1,0xb78bae46,0xb89bafd6,
0x34a53913,0xa6483732,0xbba8ba2f,0xbbffbb25,0xb78bae46,0xbac2b7e3,0xbb0ebbf6,0xb848baf6,0xbba8ba2f,0xbb50bbfa,0xb4a5b913,0x367cacb5,
0x39ed3bea,0x393a3be2,0xb95fb0b2,0xba0fb179,0xb56433c6,0xb8ec2648,0xbb88bbc3,0xba4fbbff,0xbbfeba6d,0xbb25bbce,0xaa48b8c4,0x3732b303,
0xb6d7badd,0x3444b67c,0x3b3b381d,0x3bb63b50,0x38723bd9,0x37323bce,0xbaa7b23e,0xbb25b303,0xbaa7b23e,0xbbb6b67c,0xb872bbd9,0xb444bb50,
0xb872bbd9,0xacb5ba8a,0x3aa7323e,0x3bfa389b,0x3aa7323e,0x3bf139cb,0x38723bd9,0xafd63984,0x35643bc3,0x33033bb6,0xbb88b3c6,0xbbceb444,
0xbbfeb8c4,0xbb77ba0f,0x2a48ba6d,0x35c2b93a,0x36d7b81d,0x3a8aafd6,0x3b3b3add,0x389b3bf1,0x395f3bea,0x26483b25,0xb9ed30b2,0xbbffb732,
0x2e463ba8,0xa6483b99,0xbbf6b4a5,0xbbffb505,0xba2fbb0e,0xb848bbb6,0x3913b78b,0x3ac2b444,0x3bf634a5,0x3b50393a,0x2e463ba8,0xb67c3a0f,
0xb913378b,0xbbe2afd6,0xba2fbb0e,0xb179bbf1,0xb0b23b88,0xb4443b77,0xbbeab564,0xbbb6b5c2,0xb3c6bbfe,0x2cb5bbe2,0x3bc3aa48,0x3bfa3179,
0x38c43b3b,0x2fd63bff,0xba6d36d7,0xbbf12648,0xbaddb95f,0xb505bbce,0x381db9ed,0x3b99b303,0xb61f3b64,0xb7e33b50,0xbb64b61f,0xbaf6b67c,
0x361fbb64,0x393aba8a,0x3b64361f,0x3a0f389b,0xb61f3b64,0xba4f3984,0xbb64b61f,0xb8ecb9cb,0x361fbb64,0x3b25b848,0x3b64361f,0x37323ac2,
0xb8c43b3b,0xb9843b25,0xba6db6d7,0xb9cbb732,0x3addb95f,0x3bceb7e3,0x381d39ed,0x33033af6,0xbbea3564,0xbb77acb5,0xb0b2bb88,0x35c2bbfa,
0x3bc32a48,0x389b38ec,0xb3c63bfe,0xba8a3a4f,0xba2f3b0e,0xbac23af6,0xb913b78b,0xb848b7e3,0x3bf6b4a5,0x3b50acb5,0xae463ba8,0xb67c3bfa,
0xb913b78b,0xb179ba4f,0x3a2fbb0e,0x3be2b8ec,0xae463ba8,0xb9cb3b99,0xbbf634a5,0xb984b505,0xbb3b3add,0xbb993ac2,0xb6d7b81d,0xb505b848,
0x39ed30b2,0x37e335c2,0xb95f3bea,0xbaf63b77,0x3564bbc3,0x3a0fbbe2,0x3b88b3c6,0x393a3179,0xbbfe38c4,0xba4f2648,0xaa48ba6d,0x38ecbbff,
0xbbd93aa7,0xbbfa3a8a,0xb23eb872,0xacb5b89b,0x323e3872,0xafd639cb,0xbbd93aa7,0xbbf13984,0x3bd9baa7,0x3b99b848,0x323e3872,0xb5053ac2,
0xb23eb872,0x37e3bb77,0x3bd9baa7,0x3af6b5c2,0xbbfe3a6d,0xbbe23a4f,0x2a48b8c4,0x3179b8ec,0xb6d73add,0xb9843b99,0xbb3b381d,0xb9cb3505,
0x395fb0b2,0x33033444,0xb9ed3bea,0xbbce3bb6,0x3b88bbc3,0x3b77b93a,0x356433c6,0xb5c23a0f,0xbba83a2f,0xbb503a0f,0x34a5b913,0x367cb93a,
0xbb0e3bf6,0xbbe23bf1,0xb78b2e46,0xb179afd6,0xb4a53913,0xb9cb3b25,0xbba83a2f,0xb9843732,0x378bae46,0xb30337e3,0xbb0e3bf6,0xbbce3af6,
0xbadd39ed,0xba4f39cb,0x381db95f,0x38ecb984,0xbbea3b88,0xbb253ac2,0x30b2b564,0x3732b848,0xbbc33bfe,0xbbb63b77,0xb3c62a48,0x3444b5c2,
0xba6d3b3b,0xbbfa3be2,0xb8c436d7,0x2cb5b179,0xb9a839a8,0xb8ec3984,0x39a8b9a8,0x3a4fb9cb,0xb9a839a8,0xb7323848,0x39a8b9a8,0x3b25bac2,
0xb9a839a8,0xb44435c2,0x39a8b9a8,0x3bb6bb77,0xb9a839a8,0xacb53179,0x39a8b9a8,0x3bfabbe2,0xb81d395f,0xb67c393a,0x3addb9ed,0x3b50ba0f,
0xb0b23564,0x31792fd6,0x3beabb88,0x3be2bbf1,0x33c6aa48,0x3984b732,0x3bc3bbfe,0x39cbbb25,0x38c4b6d7,0x3bcebaf6,0x3a6dbb3b,0x3303b7e3,
0xb4a53913,0xb17938ec,0x3ba8ba2f,0x3be2ba4f,0x378bae46,0x39cbb505,0x3b0ebbf6,0x3984bb99,0x3ba8ba2f,0x3bcebbb6,0x34a5b913,0xb303b444,
0x3b0ebbf6,0x35c2ba0f,0xb78b2e46,0xbb77393a,0xaa4838c4,0x2cb5389b,0x3bfeba6d,0x3bfaba8a,0x3b3bb81d,0x3bf1b984,0x36d7badd,0x2fd6b9cb,
0x39edbbea,0x3505bac2,0xb95f30b2,0xbb993848,0xb564b3c6,0xbaf635c2,0xbb883bc3,0xb7e33b77,0x323e3872,0x35053848,0x3bd9baa7,0x3b99bac2,
0x3bd9baa7,0x3af6bb77,0xb23eb872,0xb7e3b5c2,0xb23eb872,0xb93ab179,0xbbd93aa7,0xba0f3be2,0xbbd93aa7,0xb8ec3bff,0x323e3872,0x3a4fa648,
0x36d7381d,0x384837e3,0x3b3bbadd,0x3ac2baf6,0x395fbbea,0x367cbbfa,0xb9edb0b2,0xbb502cb5,0xbb8833c6,0xbbe238ec,0xb5643bc3,0x31793a4f,
0x2a483a6d,0x39843505,0x3bfeb8c4,0x39cbbb99,0x3913378b,0x39cb3732,0x3a2fbb0e,0x3984bb25,0x2e46bba8,0xb303baf6,0xbbf634a5,0xbbce37e3,
0xba2f3b0e,0xb5c23bfa,0x3913378b,0x3b772cb5,0x3bf6b4a5,0x3a8aba4f,0x2e46bba8,0xb89bb8ec,0x3a6d36d7,0x3af6367c,0x38c4bb3b,0x37e3bb50,
0xb81db9ed,0xba0fb89b,0xbadd395f,0xb93a3a8a,0x30b23b88,0x38ec39cb,0x3beab564,0x3a4fb984,0x33c6bbfe,0xb732bac2,0xbbc3aa48,0xbb253848,
0x3b64361f,0x3bb635c2,0x361fbb64,0x3444bb77,0xbb64b61f,0xbbfab179,0xb61f3b64,0xacb53be2,0x3b64361f,0x3bf1a648,0x361fbb64,0xafd6bbff,
0xbb64b61f,0xbb993303,0xb61f3b64,0x35053bce,0x3bea3564,0x3bff3505,0x30b2bb88,0x2648bb99,0xbbc32a48,0xbac23444,0x33c63bfe,0x38483bb6,
0x3a6db6d7,0x367cba0f,0xb8c4bb3b,0xbb50b93a,0xb81d39ed,0x31793bf1,0x3add395f,0x3be22fd6,0x3bf634a5,0x3bce3444,0xae46bba8,0xb303bbb6,
0xb913378b,0xb5c2393a,0x3a2f3b0e,0x3b773a0f,0xae46bba8,0xb89bbbf1,0xbbf6b4a5,0xba8a2fd6,0x3a2f3b0e,0x3bff3732,0x3913b78b,0xa648bb25,
0x3b8833c6,0x3b253303,0xb564bbc3,0xb732bbce,0xaa483a6d,0x34443b50,0x3bfe38c4,0x3bb6367c,0xbb3bbadd,0xbbfab89b,0xb6d7381d,0x2cb53a8a,
0x39edb0b2,0x2fd6b984,0xb95fbbea,0xbbf1b9cb,0x3aa7323e,0x3a0f3179,0xb872bbd9,0xb93abbe2,0x38723bd9,0x3a4f3bff,0x3aa7323e,0x38eca648,
0xbaa7b23e,0xb7323303,0x38723bd9,0x3b253bce,0xb872bbd9,0xbbb6bb50,0xbaa7b23e,0xb444367c,0x395f30b2,0x389b2fd6,0xb9edbbea,0xba8abbf1,
0x3b883bc3,0x3bff3b25,0x3564b3c6,0x2648b732,0x2a4838c4,0x38483af6,0x3bfe3a6d,0x3ac237e3,0xbb3bb81d,0xb67c2cb5,0x36d73add,0x3b503bfa,
0x378b2e46,0x35c22cb5,0xbb0ebbf6,0xbb77bbfa,0x3ba83a2f,0x3a8a38ec,0xb4a5b913,0xb89bba4f,0x3b0e3bf6,0x3bff3b99,0x378b2e46,0xa648b505,
0x34a53913,0x3ac23bb6,0x3ba83a2f,0x38483444,0x33c62a48,0x2fd62648,0xbbc3bbfe,0xbbf1bbff,0x38c436d7,0x35053303,0xba6dbb3b,0xbb99bbce,
0x3add39ed,0x37e3367c,0xb81db95f,0xbaf6bb50,0x3bea3b88,0x393a389b,0xb0b2b564,0xba0fba8a,0x3c003c00,0xbbf1bbff,0,0x2fd62648,
0x3c003c00,0xbb99bbce,0,0x35053303,0x3c003c00,0xbaf6bb50,0,0x37e3367c,0x3c003c00,0xba0fba8a,0,0x393a389b,
0x3bc33bfe,0xbb77bbfa,0xb3c6aa48,0x35c22cb5,0x3a6d3b3b,0xb89bba4f,0xb8c4b6d7,0x3a8a38ec,0x381d395f,0xa648b505,0xbaddb9ed,0x3bff3b99,
0x30b23564,0x38483444,0xbbeabb88,0x3ac23bb6,0x3b0e3bf6,0xba8abbf1,0xb78bae46,0x389b2fd6,0x34a53913,0x2648b732,0xbba8ba2f,0x3bff3b25,
0xb78bae46,0x3ac237e3,0xbb0ebbf6,0x38483af6,0xbba8ba2f,0x3b503bfa,0xb4a5b913,0xb67c2cb5,0x39ed3bea,0xb93abbe2,0xb95fb0b2,0x3a0f3179,
0xb56433c6,0x38eca648,0xbb88bbc3,0x3a4f3bff,0xbbfeba6d,0x3b253bce,0xaa48b8c4,0xb7323303,0xb6d7badd,0xb444367c,0x3b3b381d,0xbbb6bb50,
0x38723bd9,0xb732bbce,0xbaa7b23e,0x3b253303,0xbaa7b23e,0x3bb6367c,0xb872bbd9,0x34443b50,0xb872bbd9,0x2cb53a8a,0x3aa7323e,0xbbfab89b,
0x3aa7323e,0xbbf1b9cb,0x38723bd9,0x2fd6b984,0x35643bc3,0xb303bbb6,0xbb88b3c6,0x3bce3444,0xbbfeb8c4,0x3b773a0f,0x2a48ba6d,0xb5c2393a,
0x36d7b81d,0xba8a2fd6,0x3b3b3add,0xb89bbbf1,0x395f3bea,0xa648bb25,0xb9ed30b2,0x3bff3732,0x2e463ba8,0x2648bb99,0xbbf6b4a5,0x3bff3505,
0xba2fbb0e,0x38483bb6,0x3913b78b,0xbac23444,0x3bf634a5,0xbb50b93a,0x2e463ba8,0x367cba0f,0xb913378b,0x3be22fd6,0xba2fbb0e,0x31793bf1,
0xb0b23b88,0x3444bb77,0xbbeab564,0x3bb635c2,0xb3c6bbfe,0xacb53be2,0x3bc3aa48,0xbbfab179,0x38c43b3b,0xafd6bbff,0xba6d36d7,0x3bf1a648,
0xbaddb95f,0x35053bce,0x381db9ed,0xbb993303,0xb61f3b64,0x37e3bb50,0xbb64b61f,0x3af6367c,0x361fbb64,0xb93a3a8a,0x3b64361f,0xba0fb89b,
0xb61f3b64,0x3a4fb984,0xbb64b61f,0x38ec39cb,0x361fbb64,0xbb253848,0x3b64361f,0xb732bac2,0xb8c43b3b,0x3984bb25,0xba6db6d7,0x39cb3732,
0x3addb95f,0xbbce37e3,0x381d39ed,0xb303baf6,0xbbea3564,0x3b772cb5,0xb0b2bb88,0xb5c23bfa,0x3bc32a48,0xb89bb8ec,0xb3c63bfe,0x3a8aba4f,
0xba2f3b0e,0x3ac2baf6,0xb913b78b,0x384837e3,0x3bf6b4a5,0xbb502cb5,0xae463ba8,0x367cbbfa,0xb913b78b,0x31793a4f,0x3a2fbb0e,0xbbe238ec,
0xae463ba8,0x39cbbb99,0xbbf634a5,0x39843505,0xbb3b3add,0x3b99bac2,0xb6d7b81d,0x35053848,0x39ed30b2,0xb7e3b5c2,0xb95f3bea,0x3af6bb77,
0x3564bbc3,0xba0f3be2,0x3b88b3c6,0xb93ab179,0xbbfe38c4,0x3a4fa648,0xaa48ba6d,0xb8ec3bff,0xbbd93aa7,0x3bfaba8a,0xb23eb872,0x2cb5389b,
0x323e3872,0x2fd6b9cb,0xbbd93aa7,0x3bf1b984,0x3bd9baa7,0xbb993848,0x323e3872,0x3505bac2,0xb23eb872,0xb7e33b77,0x3bd9baa7,0xbaf635c2,
0xbbfe3a6d,0x3be2ba4f,0x2a48b8c4,0xb17938ec,0xb6d73add,0x3984bb99,0xbb3b381d,0x39cbb505,0x395fb0b2,0xb303b444,0xb9ed3bea,0x3bcebbb6,
0x3b88bbc3,0xbb77393a,0x356433c6,0x35c2ba0f,0xbba83a2f,0x3b50ba0f,0x34a5b913,0xb67c393a,0xbb0e3bf6,0x3be2bbf1,0xb78b2e46,0x31792fd6,
0xb4a53913,0x39cbbb25,0xbba83a2f,0x3984b732,0x378bae46,0x3303b7e3,0xbb0e3bf6,0x3bcebaf6,0xbadd39ed,0x3a4fb9cb,0x381db95f,0xb8ec3984,
0xbbea3b88,0x3b25bac2,0x30b2b564,0xb7323848,0xbbc33bfe,0x3bb6bb77,0xb3c62a48,0xb44435c2,0xba6d3b3b,0x3bfabbe2,0xb8c436d7,0xacb53179,
0xb9a839a8,0x38ecb984,0x39a8b9a8,0xba4f39cb,0xb9a839a8,0x3732b848,0x39a8b9a8,0xbb253ac2,0xb9a839a8,0x3444b5c2,0x39a8b9a8,0xbbb63b77,
0xb9a839a8,0x2cb5b179,0x39a8b9a8,0xbbfa3be2,0xb81d395f,0x367cb93a,0x3addb9ed,0xbb503a0f,0xb0b23564,0xb179afd6,0x3beabb88,0xbbe23bf1,
0x33c6aa48,0xb9843732,0x3bc3bbfe,0xb9cb3b25,0x38c4b6d7,0xbbce3af6,0x3a6dbb3b,0xb30337e3,0xb4a53913,0x3179b8ec,0x3ba8ba2f,0xbbe23a4f,
0x378bae46,0xb9cb3505,0x3b0ebbf6,0xb9843b99,0x3ba8ba2f,0xbbce3bb6,0x34a5b913,0x33033444,0x3b0ebbf6,0xb5c23a0f,0xb78b2e46,0x3b77b93a,
0xaa4838c4,0xacb5b89b,0x3bfeba6d,0xbbfa3a8a,0x3b3bb81d,0xbbf13984,0x36d7badd,0xafd639cb,0x39edbbea,0xb5053ac2,0xb95f30b2,0x3b99b848,
0xb564b3c6,0x3af6b5c2,0xbb883bc3,0x37e3bb77,0x323e3872,0xb505b848,0x3bd9baa7,0xbb993ac2,0x3bd9baa7,0xbaf63b77,0xb23eb872,0x37e335c2,
0xb23eb872,0x393a3179,0xbbd93aa7,0x3a0fbbe2,0xbbd93aa7,0x38ecbbff,0x323e3872,0xba4f2648,0x36d7381d,0xb848b7e3,0x3b3bbadd,0xbac23af6,
0x395fbbea,0xb67c3bfa,0xb9edb0b2,0x3b50acb5,0xbb8833c6,0x3be2b8ec,0xb5643bc3,0xb179ba4f,0x2a483a6d,0xb984b505,0x3bfeb8c4,0xb9cb3b99,
0x3913378b,0xb9cbb732,0x3a2fbb0e,0xb9843b25,0x2e46bba8,0x33033af6,0xbbf634a5,0x3bceb7e3,0xba2f3b0e,0x35c2bbfa,0x3913378b,0xbb77acb5,
0x3bf6b4a5,0xba8a3a4f,0x2e46bba8,0x389b38ec,0x3a6d36d7,0xbaf6b67c,0x38c4bb3b,0xb7e33b50,0xb81db9ed,0x3a0f389b,0xbadd395f,0x393aba8a,
0x30b23b88,0xb8ecb9cb,0x3beab564,0xba4f3984,0x33c6bbfe,0x37323ac2,0xbbc3aa48,0x3b25b848,0x3b64361f,0xbbb6b5c2,0x361fbb64,0xb4443b77,
0xbb64b61f,0x3bfa3179,0xb61f3b64,0x2cb5bbe2,0x3b64361f,0xbbf12648,0x361fbb64,0x2fd63bff,0xbb64b61f,0x3b99b303,0xb61f3b64,0xb505bbce,
0x3bea3564,0xbbffb505,0x30b2bb88,0xa6483b99,0xbbc32a48,0x3ac2b444,0x33c63bfe,0xb848bbb6,0x3a6db6d7,0xb67c3a0f,0xb8c4bb3b,0x3b50393a,
0xb81d39ed,0xb179bbf1,0x3add395f,0xbbe2afd6,0x3bf634a5,0xbbceb444,0xae46bba8,0x33033bb6,0xb913378b,0x35c2b93a,0x3a2f3b0e,0xbb77ba0f,
0xae46bba8,0x389b3bf1,0xbbf6b4a5,0x3a8aafd6,0x3a2f3b0e,0xbbffb732,0x3913b78b,0x26483b25,0x3b8833c6,0xbb25b303,0xb564bbc3,0x37323bce,
0xaa483a6d,0xb444bb50,0x3bfe38c4,0xbbb6b67c,0xbb3bbadd,0x3bfa389b,0xb6d7381d,0xacb5ba8a,0x39edb0b2,0xafd63984,0xb95fbbea,0x3bf139cb,
0x3aa7323e,0xba0fb179,0xb872bbd9,0x393a3be2,0x38723bd9,0xba4fbbff,0x3aa7323e,0xb8ec2648,0xbaa7b23e,0x3732b303,0x38723bd9,0xbb25bbce,
0xb872bbd9,0x3bb63b50,0xbaa7b23e,0x3444b67c,0x395f30b2,0xb89bafd6,0xb9edbbea,0x3a8a3bf1,0x3b883bc3,0xbbffbb25,0x3564b3c6,0xa6483732,
0x2a4838c4,0xb848baf6,0x3bfe3a6d,0xbac2b7e3,0xbb3bb81d,0x367cacb5,0x36d73add,0xbb50bbfa,0x378b2e46,0xb5c2acb5,0xbb0ebbf6,0x3b773bfa,
0x3ba83a2f,0xba8ab8ec,0xb4a5b913,0x389b3a4f,0x3b0e3bf6,0xbbffbb99,0x378b2e46,0x26483505,0x34a53913,0xbac2bbb6,0x3ba83a2f,0xb848b444,
0x33c62a48,0xafd6a648,0xbbc3bbfe,0x3bf13bff,0x38c436d7,0xb505b303,0xba6dbb3b,0x3b993bce,0x3add39ed,0xb7e3b67c,0xb81db95f,0x3af63b50,
0x3bea3b88,0xb93ab89b,0xb0b2b564,0x3a0f3a8a,0x3c003c00,0x38ec3984,0,0xba4fb9cb,0x3c003c00,0x37323848,0,0xbb25bac2,
0x3c003c00,0x344435c2,0,0xbbb6bb77,0x3c003c00,0x2cb53179,0,0xbbfabbe2,0xb3c6aa48,0xbb50ba0f,0xbbc3bbfe,0xb67cb93a,
0xb8c4b6d7,0xbbe2bbf1,0xba6dbb3b,0x3179afd6,0xbaddb9ed,0xb9cbbb25,0xb81db95f,0x39843732,0xbbeabb88,0xb303b7e3,0xb0b2b564,0x3bce3af6,
0xbb0ebbf6,0xb179b8ec,0x378b2e46,0x3be23a4f,0xb4a5b913,0x39cb3505,0x3ba83a2f,0x39843b99,0x378b2e46,0x3bce3bb6,0x3b0e3bf6,0xb3033444,
0x3ba83a2f,0x35c23a0f,0x34a53913,0xbb77b93a,0x395f30b2,0x3bfa3a8a,0x39ed3bea,0xacb5389b,0x3b883bc3,0x2fd639cb,0xb56433c6,0xbbf1b984,
0x2a4838c4,0xbb99b848,0xbbfeba6d,0xb505bac2,0xbb3bb81d,0xb7e3bb77,0xb6d7badd,0x3af635c2,0x38723bd9,0xb5053848,0xbaa7b23e,0xbb99bac2,
0xbaa7b23e,0xbaf6bb77,0xb872bbd9,0x37e3b5c2,0xb872bbd9,0x393ab179,0x3aa7323e,0x3a0f3be2,0x3aa7323e,0x38ec3bff,0x38723bd9,0xba4fa648,
0xbb88b3c6,0xbac2baf6,0xb564bbc3,0x3848b7e3,0x2a48ba6d,0x3b502cb5,0x3bfe38c4,0x367c3bfa,0x3b3b3add,0xb1793a4f,0xb6d7381d,0xbbe2b8ec,
0xb9ed30b2,0xb9cbbb99,0xb95fbbea,0x3984b505,0xae46bba8,0x39cbb732,0x3bf634a5,0x39843b25,0x3a2f3b0e,0xb3033af6,0xb913378b,0xbbceb7e3,
0xbbf6b4a5,0xb5c2bbfa,0xae46bba8,0x3b77acb5,0x3913b78b,0x3a8a3a4f,0x3a2f3b0e,0xb89b38ec,0x3bea3564,0x37e33b50,0xb0b23b88,0xbaf6367c,
0xbbc32a48,0xb93aba8a,0xb3c6bbfe,0x3a0fb89b,0x3a6db6d7,0x3a4f3984,0x38c43b3b,0xb8ec39cb,0xb81d39ed,0xbb25b848,0xbaddb95f,0x3732bac2,
0xb61f3b64,0xbbb635c2,0xbb64b61f,0xb444bb77,0x361fbb64,0x3bfab179,0x3b64361f,0x2cb53be2,0xb61f3b64,0xbbf1a648,0xbb64b61f,0x2fd6bbff,
0x361fbb64,0x3b993303,0x3b64361f,0xb5053bce,0xba6db6d7,0xa648bb99,0x38c4bb3b,0x3bffb505,0x381d39ed,0xb8483bb6,0xbadd395f,0xbac2b444,
0xb0b2bb88,0x3b50b93a,0x3beab564,0x367c3a0f,0xb3c63bfe,0xbbe22fd6,0xbbc3aa48,0x3179bbf1,0x3a2fbb0e,0x3bceb444,0x3913378b,0xb3033bb6,
0xbbf634a5,0xb5c2b93a,0x2e46bba8,0x3b77ba0f,0x3913378b,0xb89b3bf1,0xba2f3b0e,0xba8aafd6,0x2e46bba8,0x3bffb732,0x3bf6b4a5,0xa6483b25,
0x36d7381d,0xb7323bce,0xbb3b3add,0xbb253303,0x395fbbea,0x3bb6b67c,0x39ed30b2,0xb4443b50,0xbb8833c6,0x2cb5ba8a,0x3564bbc3,0x3bfab89b,
0x2a483a6d,0xbbf139cb,0xbbfe38c4,0xafd6b984,0xbbd93aa7,0xba0f3179,0xb23eb872,0x393abbe2,0x323e3872,0xba4f3bff,0xbbd93aa7,0xb8eca648,
0x3bd9baa7,0x37323303,0x323e3872,0xbb253bce,0xb23eb872,0x3bb6bb50,0x3bd9baa7,0x3444367c,0x2a48b8c4,0x3a8abbf1,0x3bfeba6d,0x389bafd6,
0xbb3b381d,0xa648b732,0x36d7badd,0x3bffbb25,0xb9ed3bea,0xbac237e3,0xb95f30b2,0x3848baf6,0x356433c6,0xbb503bfa,0xbb883bc3,0xb67cacb5,
0x3ba8ba2f,0x35c2acb5,0xb4a53913,0xbb773bfa,0x3b0ebbf6,0x3a8ab8ec,0x378bae46,0xb89b3a4f,0x34a5b913,0x3bffbb99,0x3ba8ba2f,0xa6483505,
0xb78b2e46,0x3ac2bbb6,0x3b0ebbf6,0x3848b444,0xb81d395f,0xbbf13bff,0xbadd39ed,0xafd62648,0xb0b23564,0xbb993bce,0xbbea3b88,0xb5053303,
0x33c6aa48,0xbaf63b50,0xbbc33bfe,0xb7e3367c,0x38c4b6d7,0xba0f3a8a,0xba6d3b3b,0xb93a389b,0xb9a839a8,0x2fd6a648,0x39a8b9a8,0x3bf1bbff,
0xb9a839a8,0x3505b303,0x39a8b9a8,0x3b99bbce,0xb9a839a8,0x37e3b67c,0x39a8b9a8,0x3af6bb50,0xb9a839a8,0x393ab89b,0x39a8b9a8,0x3a0fba8a,
0x3addb9ed,0x3b77bbfa,0x381db95f,0xb5c22cb5,0x3beabb88,0x389bba4f,0x30b2b564,0xba8a38ec,0x3bc3bbfe,0x2648b505,0xb3c62a48,0xbbff3b99,
0x3a6dbb3b,0xb8483444,0xb8c436d7,0xbac23bb6,0x34a5b913,0xb89b2fd6,0xbba83a2f,0xba8a3bf1,0xb78b2e46,0xbbff3b25,0xbb0e3bf6,0x26483732,
0xbba83a2f,0xb8483af6,0xb4a53913,0x3ac2b7e3,0xbb0e3bf6,0x367c2cb5,0x378bae46,0x3b50bbfa,0xbbfe3a6d,0xb93a3be2,0xaa4838c4,0x3a0fb179,
0xb6d73add,0x38ec2648,0x3b3bb81d,0x3a4fbbff,0x395fb0b2,0x3b25bbce,0x39edbbea,0xb732b303,0x3b88bbc3,0xb444b67c,0xb564b3c6,0xbbb63b50,
0x323e3872,0x3b25b303,0x3bd9baa7,0x3732bbce,0x3bd9baa7,0x3444bb50,0xb23eb872,0xbbb6367c,0xb23eb872,0xbbfa389b,0xbbd93aa7,0xacb53a8a,
0xbbd93aa7,0x2fd63984,0x323e3872,0x3bf1b9cb,0x3b3bbadd,0x3303bbb6,0xb6d7b81d,0xbbce3444,0xb9edb0b2,0xbb773a0f,0xb95f3bea,0x35c2393a,
0xb5643bc3,0x3a8a2fd6,0x3b88b3c6,0x389bbbf1,0x3bfeb8c4,0x2648bb25,0xaa48ba6d,0xbbff3732,0xb913b78b,0xbbff3505,0xba2f3b0e,0x26483b99,
0xae463ba8,0x3ac23444,0x3bf6b4a5,0x3848bbb6,0x3a2fbb0e,0xb67cba0f,0xb913b78b,0xbb50393a,0xbbf634a5,0xb1793bf1,0xae463ba8,0x3be2afd6,
0xb8c43b3b,0x34443b77,0x3a6d36d7,0x3bb6b5c2,0x3addb95f,0xacb5bbe2,0xb81db9ed,0xbbfa3179,0xbbea3564,0xafd63bff,0x30b23b88,0x3bf12648,
0x3bc32a48,0x3505bbce,0x33c6bbfe,0xbb99b303,0x3b64361f,0x3af6b67c,0x361fbb64,0xb7e3bb50,0xbb64b61f,0xba0f389b,0xb61f3b64,0x393a3a8a,
0x3b64361f,0x38ecb9cb,0x361fbb64,0xba4fb984,0xbb64b61f,0xb7323ac2,0xb61f3b64,0x3b253848,0x30b2bb88,0xb984bb25,0xbbeab564,0xb9cb3732,
0x33c63bfe,0x3bce37e3,0x3bc3aa48,0x3303baf6,0xb8c4bb3b,0xbb772cb5,0xba6d36d7,0x35c23bfa,0x3add395f,0x389bb8ec,0x381db9ed,0xba8aba4f,
0xbbf6b4a5,0xb84837e3,0x2e463ba8,0x3ac23af6,0x3913b78b,0xb67cbbfa,0xba2fbb0e,0xbb50acb5,0x2e463ba8,0x3be238ec,0x3bf634a5,0x3179ba4f,
0xba2fbb0e,0xb9843505,0xb913378b,0x39cb3b99,0x35643bc3,0x3b993ac2,0x3b8833c6,0x3505b848,0xbbfeb8c4,0xb7e335c2,0xaa483a6d,0x3af63b77,
0x36d7b81d,0xba0fbbe2,0xbb3bbadd,0xb93a3179,0x395f3bea,0x3a4f2648,0x39edb0b2,0xb8ecbbff,0x3aa7323e,0x2cb5b89b,0xb872bbd9,0xbbfaba8a,
0x38723bd9,0x3bf13984,0x3aa7323e,0xafd6b9cb,0xbaa7b23e,0x35053ac2,0x38723bd9,0x3b993848,0xb872bbd9,0xbaf6b5c2,0xbaa7b23e,0x37e33b77,
0xb9edbbea,0xbbe2ba4f,0xb95fb0b2,0x317938ec,0x3564b3c6,0xb984bb99,0xbb88bbc3,0xb9cbb505,0x3bfe3a6d,0x3303b444,0xaa48b8c4,0xbbcebbb6,
0x36d73add,0x3b77393a,0x3b3b381d,0xb5c2ba0f,0xb78bae46,0x367c393a,0x3b0e3bf6,0x3b503a0f,0xbba8ba2f,0xb1792fd6,0x34a53913,0x3be23bf1,
0xbb0ebbf6,0xb984b732,0xb78bae46,0x39cb3b25,0xb4a5b913,0xbbcebaf6,0xbba8ba2f,0x330337e3,0x3bc33bfe,0x3a4f39cb,0x33c62a48,0xb8ecb984,
0x3a6d3b3b,0x3b253ac2,0x38c436d7,0xb732b848,0x381d395f,0x3bb63b77,0x3add39ed,0xb444b5c2,0x30b23564,0x3bfa3be2,0x3bea3b88,0xacb5b179,
0x3c003c00,0xb8ecb984,0,0x3a4f39cb,0x3c003c00,0xb732b848,0,0x3b253ac2,0x3c003c00,0xb444b5c2,0,0x3bb63b77,
0x3c003c00,0xacb5b179,0,0x3bfa3be2,0xb3c6aa48,0x3b503a0f,0xbbc3bbfe,0x367c393a,0xb8c4b6d7,0x3be23bf1,0xba6dbb3b,0xb1792fd6,
0xbaddb9ed,0x39cb3b25,0xb81db95f,0xb984b732,0xbbeabb88,0x330337e3,0xb0b2b564,0xbbcebaf6,0xbb0ebbf6,0x317938ec,0x378b2e46,0xbbe2ba4f,
0xb4a5b913,0xb9cbb505,0x3ba83a2f,0xb984bb99,0x378b2e46,0xbbcebbb6,0x3b0e3bf6,0x3303b444,0x3ba83a2f,0xb5c2ba0f,0x34a53913,0x3b77393a,
0x395f30b2,0xbbfaba8a,0x39ed3bea,0x2cb5b89b,0x3b883bc3,0xafd6b9cb,0xb56433c6,0x3bf13984,0x2a4838c4,0x3b993848,0xbbfeba6d,0x35053ac2,
0xbb3bb81d,0x37e33b77,0xb6d7badd,0xbaf6b5c2,0x38723bd9,0x3505b848,0xbaa7b23e,0x3b993ac2,0xbaa7b23e,0x3af63b77,0xb872bbd9,0xb7e335c2,
0xb872bbd9,0xb93a3179,0x3aa7323e,0xba0fbbe2,0x3aa7323e,0xb8ecbbff,0x38723bd9,0x3a4f2648,0xbb88b3c6,0x3ac23af6,0xb564bbc3,0xb84837e3,
0x2a48ba6d,0xbb50acb5,0x3bfe38c4,0xb67cbbfa,0x3b3b3add,0x3179ba4f,0xb6d7381d,0x3be238ec,0xb9ed30b2,0x39cb3b99,0xb95fbbea,0xb9843505,
0xae46bba8,0xb9cb3732,0x3bf634a5,0xb984bb25,0x3a2f3b0e,0x3303baf6,0xb913378b,0x3bce37e3,0xbbf6b4a5,0x35c23bfa,0xae46bba8,0xbb772cb5,
0x3913b78b,0xba8aba4f,0x3a2f3b0e,0x389bb8ec,0x3bea3564,0xb7e3bb50,0xb0b23b88,0x3af6b67c,0xbbc32a48,0x393a3a8a,0xb3c6bbfe,0xba0f389b,
0x3a6db6d7,0xba4fb984,0x38c43b3b,0x38ecb9cb,0xb81d39ed,0x3b253848,0xbaddb95f,0xb7323ac2,0xb61f3b64,0x3bb6b5c2,0xbb64b61f,0x34443b77,
0x361fbb64,0xbbfa3179,0x3b64361f,0xacb5bbe2,0xb61f3b64,0x3bf12648,0xbb64b61f,0xafd63bff,0x361fbb64,0xbb99b303,0x3b64361f,0x3505bbce,
0xba6db6d7,0x26483b99,0x38c4bb3b,0xbbff3505,0x381d39ed,0x3848bbb6,0xbadd395f,0x3ac23444,0xb0b2bb88,0xbb50393a,0x3beab564,0xb67cba0f,
0xb3c63bfe,0x3be2afd6,0xbbc3aa48,0xb1793bf1,0x3a2fbb0e,0xbbce3444,0x3913378b,0x3303bbb6,0xbbf634a5,0x35c2393a,0x2e46bba8,0xbb773a0f,
0x3913378b,0x389bbbf1,0xba2f3b0e,0x3a8a2fd6,0x2e46bba8,0xbbff3732,0x3bf6b4a5,0x2648bb25,0x36d7381d,0x3732bbce,0xbb3b3add,0x3b25b303,
0x395fbbea,0xbbb6367c,0x39ed30b2,0x3444bb50,0xbb8833c6,0xacb53a8a,0x3564bbc3,0xbbfa389b,0x2a483a6d,0x3bf1b9cb,0xbbfe38c4,0x2fd63984,
0xbbd93aa7,0x3a0fb179,0xb23eb872,0xb93a3be2,0x323e3872,0x3a4fbbff,0xbbd93aa7,0x38ec2648,0x3bd9baa7,0xb732b303,0x323e3872,0x3b25bbce,
0xb23eb872,0xbbb63b50,0x3bd9baa7,0xb444b67c,0x2a48b8c4,0xba8a3bf1,0x3bfeba6d,0xb89b2fd6,0xbb3b381d,0x26483732,0x36d7badd,0xbbff3b25,
0xb9ed3bea,0x3ac2b7e3,0xb95f30b2,0xb8483af6,0x356433c6,0x3b50bbfa,0xbb883bc3,0x367c2cb5,0x3ba8ba2f,0xb5c22cb5,0xb4a53913,0x3b77bbfa,
0x3b0ebbf6,0xba8a38ec,0x378bae46,0x389bba4f,0x34a5b913,0xbbff3b99,0x3ba8ba2f,0x2648b505,0xb78b2e46,0xbac23bb6,0x3b0ebbf6,0xb8483444,
0xb81d395f,0x3bf1bbff,0xbadd39ed,0x2fd6a648,0xb0b23564,0x3b99bbce,0xbbea3b88,0x3505b303,0x33c6aa48,0x3af6bb50,0xbbc33bfe,0x37e3b67c,
0x38c4b6d7,0x3a0fba8a,0xba6d3b3b,0x393ab89b,0xb9a839a8,0xafd62648,0x39a8b9a8,0xbbf13bff,0xb9a839a8,0xb5053303,0x39a8b9a8,0xbb993bce,
0xb9a839a8,0xb7e3367c,0x39a8b9a8,0xbaf63b50,0xb9a839a8,0xb93a389b,0x39a8b9a8,0xba0f3a8a,0x3addb9ed,0xbb773bfa,0x381db95f,0x35c2acb5,
0x3beabb88,0xb89b3a4f,0x30b2b564,0x3a8ab8ec,0x3bc3bbfe,0xa6483505,0xb3c62a48,0x3bffbb99,0x3a6dbb3b,0x3848b444,0xb8c436d7,0x3ac2bbb6,
0x34a5b913,0x389bafd6,0xbba83a2f,0x3a8abbf1,0xb78b2e46,0x3bffbb25,0xbb0e3bf6,0xa648b732,0xbba83a2f,0x3848baf6,0xb4a53913,0xbac237e3,
0xbb0e3bf6,0xb67cacb5,0x378bae46,0xbb503bfa,0xbbfe3a6d,0x393abbe2,0xaa4838c4,0xba0f3179,0xb6d73add,0xb8eca648,0x3b3bb81d,0xba4f3bff,
0x395fb0b2,0xbb253bce,0x39edbbea,0x37323303,0x3b88bbc3,0x3444367c,0xb564b3c6,0x3bb6bb50,0x323e3872,0xbb253303,0x3bd9baa7,0xb7323bce,
0x3bd9baa7,0xb4443b50,0xb23eb872,0x3bb6b67c,0xb23eb872,0x3bfab89b,0xbbd93aa7,0x2cb5ba8a,0xbbd93aa7,0xafd6b984,0x323e3872,0xbbf139cb,
0x3b3bbadd,0xb3033bb6,0xb6d7b81d,0x3bceb444,0xb9edb0b2,0x3b77ba0f,0xb95f3bea,0xb5c2b93a,0xb5643bc3,0xba8aafd6,0x3b88b3c6,0xb89b3bf1,
0x3bfeb8c4,0xa6483b25,0xaa48ba6d,0x3bffb732,0xb913b78b,0x3bffb505,0xba2f3b0e,0xa648bb99,0xae463ba8,0xbac2b444,0x3bf6b4a5,0xb8483bb6,
0x3a2fbb0e,0x367c3a0f,0xb913b78b,0x3b50b93a,0xbbf634a5,0x3179bbf1,0xae463ba8,0xbbe22fd6,0xb8c43b3b,0xb444bb77,0x3a6d36d7,0xbbb635c2,
0x3addb95f,0x2cb53be2,0xb81db9ed,0x3bfab179,0xbbea3564,0x2fd6bbff,0x30b23b88,0xbbf1a648,0x3bc32a48,0xb5053bce,0x33c6bbfe,0x3b993303,
0x3b64361f,0xbaf6367c,0x361fbb64,0x37e33b50,0xbb64b61f,0x3a0fb89b,0xb61f3b64,0xb93aba8a,0x3b64361f,0xb8ec39cb,0x361fbb64,0x3a4f3984,
0xbb64b61f,0x3732bac2,0xb61f3b64,0xbb25b848,0x30b2bb88,0x39843b25,0xbbeab564,0x39cbb732,0x33c63bfe,0xbbceb7e3,0x3bc3aa48,0xb3033af6,
0xb8c4bb3b,0x3b77acb5,0xba6d36d7,0xb5c2bbfa,0x3add395f,0xb89b38ec,0x381db9ed,0x3a8a3a4f,0xbbf6b4a5,0x3848b7e3,0x2e463ba8,0xbac2baf6,
0x3913b78b,0x367c3bfa,0xba2fbb0e,0x3b502cb5,0x2e463ba8,0xbbe2b8ec,0x3bf634a5,0xb1793a4f,0xba2fbb0e,0x3984b505,0xb913378b,0xb9cbbb99,
0x35643bc3,0xbb99bac2,0x3b8833c6,0xb5053848,0xbbfeb8c4,0x37e3b5c2,0xaa483a6d,0xbaf6bb77,0x36d7b81d,0x3a0f3be2,0xbb3bbadd,0x393ab179,
0x395f3bea,0xba4fa648,0x39edb0b2,0x38ec3bff,0x3aa7323e,0xacb5389b,0xb872bbd9,0x3bfa3a8a,0x38723bd9,0xbbf1b984,0x3aa7323e,0x2fd639cb,
0xbaa7b23e,0xb505bac2,0x38723bd9,0xbb99b848,0xb872bbd9,0x3af635c2,0xbaa7b23e,0xb7e3bb77,0xb9edbbea,0x3be23a4f,0xb95fb0b2,0xb179b8ec,
0x3564b3c6,0x39843b99,0xbb88bbc3,0x39cb3505,0x3bfe3a6d,0xb3033444,0xaa48b8c4,0x3bce3bb6,0x36d73add,0xbb77b93a,0x3b3b381d,0x35c23a0f,
0xb78bae46,0xb67cb93a,0x3b0e3bf6,0xbb50ba0f,0xbba8ba2f,0x3179afd6,0x34a53913,0xbbe2bbf1,0xbb0ebbf6,0x39843732,0xb78bae46,0xb9cbbb25,
0xb4a5b913,0x3bce3af6,0xbba8ba2f,0xb303b7e3,0x3bc33bfe,0xba4fb9cb,0x33c62a48,0x38ec3984,0x3a6d3b3b,0xbb25bac2,0x38c436d7,0x37323848,
0x381d395f,0xbbb6bb77,0x3add39ed,0x344435c2,0x30b23564,0xbbfabbe2,0x3bea3b88,0x2cb53179,0x3c003c00,0xafd6a648,0,0xbbf1bbff,
0x3c003c00,0xb505b303,0,0xbb99bbce,0x3c003c00,0xb7e3b67c,0,0xbaf6bb50,0x3c003c00,0xb93ab89b,0,0xba0fba8a,
0xbbc3bbfe,0x35c22cb5,0x33c62a48,0x3b773bfa,0xba6dbb3b,0x3a8a38ec,0x38c436d7,0x389b3a4f,0xb81db95f,0x3bff3b99,0x3add39ed,0x26483505,
0xb0b2b564,0x3ac23bb6,0x3bea3b88,0xb848b444,0x3b0e3bf6,0xb89bafd6,0xb78bae46,0xba8abbf1,0x34a53913,0xbbffbb25,0xbba8ba2f,0x2648b732,
0xb78bae46,0xb848baf6,0xbb0ebbf6,0x3ac237e3,0xbba8ba2f,0x367cacb5,0xb4a5b913,0x3b503bfa,0xb9edbbea,0x3a0f3179,0x395f30b2,0x393a3be2,
0x3564b3c6,0x3a4f3bff,0x3b883bc3,0xb8ec2648,0x3bfe3a6d,0xb7323303,0x2a4838c4,0xbb25bbce,0x36d73add,0xbbb6bb50,0xbb3bb81d,0x3444b67c,
0x38723bd9,0xbb25b303,0xbaa7b23e,0xb732bbce,0xbaa7b23e,0xb444bb50,0xb872bbd9,0x3bb6367c,0xb872bbd9,0x3bfa389b,0x3aa7323e,0x2cb53a8a,
0x3aa7323e,0xafd63984,0x38723bd9,0xbbf1b9cb,0xb564bbc3,0x3bce3444,0x3b8833c6,0x33033bb6,0x3bfe38c4,0xb5c2393a,0xaa483a6d,0xbb77ba0f,
0xb6d7381d,0xb89bbbf1,0xbb3bbadd,0x3a8aafd6,0xb95fbbea,0x3bff3732,0x39edb0b2,0x26483b25,0x2e463ba8,0xbbffb505,0xbbf6b4a5,0x2648bb99,
0xba2fbb0e,0x3ac2b444,0x3913b78b,0x38483bb6,0x3bf634a5,0xb67c3a0f,0x2e463ba8,0xbb50b93a,0xb913378b,0xb179bbf1,0xba2fbb0e,0x3be22fd6,
0x30b2bb88,0x3bb635c2,0x3bea3564,0xb4443b77,0x33c63bfe,0xbbfab179,0xbbc32a48,0x2cb5bbe2,0xb8c4bb3b,0x3bf1a648,0x3a6db6d7,0x2fd63bff,
0x3add395f,0xbb993303,0xb81d39ed,0xb505bbce,0xb61f3b64,0xbaf6b67c,0xbb64b61f,0x37e3bb50,0x361fbb64,0x3a0f389b,0x3b64361f,0xb93a3a8a,
0xb61f3b64,0xb8ecb9cb,0xbb64b61f,0x3a4fb984,0x361fbb64,0x37323ac2,0x3b64361f,0xbb253848,0x38c4bb3b,0x39cb3732,0x3a6d36d7,0xb9843b25,
0xbadd395f,0xb303baf6,0xb81db9ed,0x3bceb7e3,0x3beab564,0xb5c23bfa,0x30b23b88,0xbb77acb5,0xbbc3aa48,0x3a8aba4f,0x33c6bbfe,0x389b38ec,
0xba2f3b0e,0xb848b7e3,0xb913b78b,0x3ac2baf6,0x3bf6b4a5,0xb67c3bfa,0xae463ba8,0xbb502cb5,0xb913b78b,0x3be2b8ec,0x3a2fbb0e,0x31793a4f,
0xae463ba8,0xb984b505,0xbbf634a5,0x39cbbb99,0x3b3bbadd,0x35053848,0x36d7381d,0xbb993ac2,0xb9edb0b2,0x3af6bb77,0x395fbbea,0x37e335c2,
0xb5643bc3,0xb93ab179,0xbb8833c6,0x3a0fbbe2,0x3bfeb8c4,0xb8ec3bff,0x2a483a6d,0xba4f2648,0xbbd93aa7,0xacb5b89b,0xb23eb872,0x3bfaba8a,
0x323e3872,0xbbf13984,0xbbd93aa7,0x2fd6b9cb,0x3bd9baa7,0xb5053ac2,0x323e3872,0xbb993848,0xb23eb872,0x3af6b5c2,0x3bd9baa7,0xb7e33b77,
0x3bfeba6d,0xb17938ec,0xaa4838c4,0xbbe23a4f,0x36d7badd,0x39cbb505,0x3b3bb81d,0xb9843b99,0xb95f30b2,0x3bcebbb6,0x39edbbea,0x33033444,
0xbb883bc3,0x35c2ba0f,0xb564b3c6,0x3b77b93a,0xbba83a2f,0x367cb93a,0x34a5b913,0x3b50ba0f,0xbb0e3bf6,0xb179afd6,0xb78b2e46,0x3be2bbf1,
0xb4a53913,0xb9843732,0xbba83a2f,0x39cbbb25,0x378bae46,0xbbce3af6,0xbb0e3bf6,0x3303b7e3,0x3addb9ed,0xb8ec3984,0xb81d395f,0xba4f39cb,
0x3beabb88,0xb7323848,0xb0b23564,0xbb253ac2,0x3bc3bbfe,0xb44435c2,0x33c6aa48,0xbbb63b77,0x3a6dbb3b,0xacb53179,0x38c4b6d7,0xbbfa3be2,
0xb9a839a8,0x3a4fb9cb,0x39a8b9a8,0x38ecb984,0xb9a839a8,0x3b25bac2,0x39a8b9a8,0x3732b848,0xb9a839a8,0x3bb6bb77,0x39a8b9a8,0x3444b5c2,
0xb9a839a8,0x3bfabbe2,0x39a8b9a8,0x2cb5b179,0x381db95f,0xbb503a0f,0xbadd39ed,0xb67c393a,0x30b2b564,0xbbe23bf1,0xbbea3b88,0x31792fd6,
0xb3c62a48,0xb9cb3b25,0xbbc33bfe,0x3984b732,0xb8c436d7,0xb30337e3,0xba6d3b3b,0x3bcebaf6,0xb4a53913,0x3be2ba4f,0x3ba8ba2f,0x3179b8ec,
0x378bae46,0x3984bb99,0x3b0ebbf6,0xb9cb3505,0x3ba8ba2f,0xb303b444,0x34a5b913,0xbbce3bb6,0x3b0ebbf6,0xbb77393a,0xb78b2e46,0xb5c23a0f,
0x2a48b8c4,0xbbfa3a8a,0xbbfe3a6d,0x2cb5389b,0xbb3b381d,0xafd639cb,0xb6d73add,0x3bf1b984,0xb9ed3bea,0x3b99b848,0x395fb0b2,0x3505bac2,
0x356433c6,0x37e3bb77,0x3b88bbc3,0xbaf635c2,0x323e3872,0x3b99bac2,0x3bd9baa7,0xb505b848,0x3bd9baa7,0xb7e3b5c2,0xb23eb872,0xbaf63b77,
0xb23eb872,0xba0f3be2,0xbbd93aa7,0x393a3179,0xbbd93aa7,0x3a4fa648,0x323e3872,0x38ecbbff,0xb6d7b81d,0xbac23af6,0xbb3b3add,0x384837e3,
0xb95f3bea,0x3b50acb5,0x39ed30b2,0x367cbbfa,0x3b88b3c6,0xb179ba4f,0x3564bbc3,0xbbe238ec,0xaa48ba6d,0xb9cb3b99,0xbbfe38c4,0x39843505,
0x3913378b,0x3984bb25,0x3a2fbb0e,0xb9cbb732,0x2e46bba8,0xbbce37e3,0xbbf634a5,0x33033af6,0xba2f3b0e,0x3b772cb5,0x3913378b,0x35c2bbfa,
0x3bf6b4a5,0xb89bb8ec,0x2e46bba8,0xba8a3a4f,0xba6db6d7,0xb7e33b50,0xb8c43b3b,0x3af6367c,0x381d39ed,0x393aba8a,0x3addb95f,0xba0fb89b,
0xb0b2bb88,0xba4f3984,0xbbea3564,0x38ec39cb,0xb3c63bfe,0x3b25b848,0x3bc32a48,0xb732bac2,0x3b64361f,0x3444bb77,0x361fbb64,0xbbb6b5c2,
0xbb64b61f,0xacb53be2,0xb61f3b64,0x3bfa3179,0x3b64361f,0xafd6bbff,0x361fbb64,0xbbf12648,0xbb64b61f,0x35053bce,0xb61f3b64,0x3b99b303,
0xbbeab564,0xa6483b99,0xb0b23b88,0x3bff3505,0x3bc3aa48,0xb848bbb6,0xb3c6bbfe,0xbac23444,0xba6d36d7,0x3b50393a,0x38c43b3b,0x367cba0f,
0x381db9ed,0xbbe2afd6,0xbaddb95f,0x31793bf1,0x3bf634a5,0xb303bbb6,0xae46bba8,0xbbceb444,0xb913378b,0x3b773a0f,0x3a2f3b0e,0x35c2b93a,
0xae46bba8,0xba8a2fd6,0xbbf6b4a5,0x389b3bf1,0x3a2f3b0e,0xa648bb25,0x3913b78b,0xbbffb732,0xbb88b3c6,0x37323bce,0x35643bc3,0x3b253303,
0x2a48ba6d,0xbbb6b67c,0xbbfeb8c4,0x34443b50,0x3b3b3add,0xacb5ba8a,0x36d7b81d,0xbbfab89b,0xb9ed30b2,0x3bf139cb,0x395f3bea,0x2fd6b984,
0x3aa7323e,0xb93abbe2,0xb872bbd9,0xba0fb179,0x38723bd9,0x38eca648,0x3aa7323e,0xba4fbbff,0xbaa7b23e,0x3b253bce,0x38723bd9,0x3732b303,
0xb872bbd9,0xb444367c,0xbaa7b23e,0x3bb63b50,0xb95fb0b2,0x3a8a3bf1,0x39ed3bea,0x389b2fd6,0xbb88bbc3,0xa6483732,0xb56433c6,0x3bff3b25,
0xaa48b8c4,0xbac2b7e3,0xbbfeba6d,0x38483af6,0x3b3b381d,0xbb50bbfa,0xb6d7badd,0xb67c2cb5,0x378b2e46,0xbb77bbfa,0xbb0ebbf6,0xb5c2acb5,
0x3ba83a2f,0xb89bba4f,0xb4a5b913,0xba8ab8ec,0x3b0e3bf6,0xa648b505,0x378b2e46,0xbbffbb99,0x34a53913,0x38483444,0x3ba83a2f,0xbac2bbb6,
0xb3c6aa48,0x3bf13bff,0x3bc33bfe,0x2fd62648,0xb8c4b6d7,0x3b993bce,0x3a6d3b3b,0x35053303,0xbaddb9ed,0x3af63b50,0x381d395f,0x37e3367c,
0xbbeabb88,0x3a0f3a8a,0x30b23564,0x393a389b,0x3c003c00,0x2fd62648,0,0x3bf13bff,0x3c003c00,0x35053303,0,0x3b993bce,
0x3c003c00,0x37e3367c,0,0x3af63b50,0x3c003c00,0x393a389b,0,0x3a0f3a8a,0xbbc3bbfe,0xb5c2acb5,0x33c62a48,0xbb77bbfa,
0xba6dbb3b,0xba8ab8ec,0x38c436d7,0xb89bba4f,0xb81db95f,0xbbffbb99,0x3add39ed,0xa648b505,0xb0b2b564,0xbac2bbb6,0x3bea3b88,0x38483444,
0x3b0e3bf6,0x389b2fd6,0xb78bae46,0x3a8a3bf1,0x34a53913,0x3bff3b25,0xbba8ba2f,0xa6483732,0xb78bae46,0x38483af6,0xbb0ebbf6,0xbac2b7e3,
0xbba8ba2f,0xb67c2cb5,0xb4a5b913,0xbb50bbfa,0xb9edbbea,0xba0fb179,0x395f30b2,0xb93abbe2,0x3564b3c6,0xba4fbbff,0x3b883bc3,0x38eca648,
0x3bfe3a6d,0x3732b303,0x2a4838c4,0x3b253bce,0x36d73add,0x3bb63b50,0xbb3bb81d,0xb444367c,0x38723bd9,0x3b253303,0xbaa7b23e,0x37323bce,
0xbaa7b23e,0x34443b50,0xb872bbd9,0xbbb6b67c,0xb872bbd9,0xbbfab89b,0x3aa7323e,0xacb5ba8a,0x3aa7323e,0x2fd6b984,0x38723bd9,0x3bf139cb,
0xb564bbc3,0xbbceb444,0x3b8833c6,0xb303bbb6,0x3bfe38c4,0x35c2b93a,0xaa483a6d,0x3b773a0f,0xb6d7381d,0x389b3bf1,0xbb3bbadd,0xba8a2fd6,
0xb95fbbea,0xbbffb732,0x39edb0b2,0xa648bb25,0x2e463ba8,0x3bff3505,0xbbf6b4a5,0xa6483b99,0xba2fbb0e,0xbac23444,0x3913b78b,0xb848bbb6,
0x3bf634a5,0x367cba0f,0x2e463ba8,0x3b50393a,0xb913378b,0x31793bf1,0xba2fbb0e,0xbbe2afd6,0x30b2bb88,0xbbb6b5c2,0x3bea3564,0x3444bb77,
0x33c63bfe,0x3bfa3179,0xbbc32a48,0xacb53be2,0xb8c4bb3b,0xbbf12648,0x3a6db6d7,0xafd6bbff,0x3add395f,0x3b99b303,0xb81d39ed,0x35053bce,
0xb61f3b64,0x3af6367c,0xbb64b61f,0xb7e33b50,0x361fbb64,0xba0fb89b,0x3b64361f,0x393aba8a,0xb61f3b64,0x38ec39cb,0xbb64b61f,0xba4f3984,
0x361fbb64,0xb732bac2,0x3b64361f,0x3b25b848,0x38c4bb3b,0xb9cbb732,0x3a6d36d7,0x3984bb25,0xbadd395f,0x33033af6,0xb81db9ed,0xbbce37e3,
0x3beab564,0x35c2bbfa,0x30b23b88,0x3b772cb5,0xbbc3aa48,0xba8a3a4f,0x33c6bbfe,0xb89bb8ec,0xba2f3b0e,0x384837e3,0xb913b78b,0xbac23af6,
0x3bf6b4a5,0x367cbbfa,0xae463ba8,0x3b50acb5,0xb913b78b,0xbbe238ec,0x3a2fbb0e,0xb179ba4f,0xae463ba8,0x39843505,0xbbf634a5,0xb9cb3b99,
0x3b3bbadd,0xb505b848,0x36d7381d,0x3b99bac2,0xb9edb0b2,0xbaf63b77,0x395fbbea,0xb7e3b5c2,0xb5643bc3,0x393a3179,0xbb8833c6,0xba0f3be2,
0x3bfeb8c4,0x38ecbbff,0x2a483a6d,0x3a4fa648,0xbbd93aa7,0x2cb5389b,0xb23eb872,0xbbfa3a8a,0x323e3872,0x3bf1b984,0xbbd93aa7,0xafd639cb,
0x3bd9baa7,0x3505bac2,0x323e3872,0x3b99b848,0xb23eb872,0xbaf635c2,0x3bd9baa7,0x37e3bb77,0x3bfeba6d,0x3179b8ec,0xaa4838c4,0x3be2ba4f,
0x36d7badd,0xb9cb3505,0x3b3bb81d,0x3984bb99,0xb95f30b2,0xbbce3bb6,0x39edbbea,0xb303b444,0xbb883bc3,0xb5c23a0f,0xb564b3c6,0xbb77393a,
0xbba83a2f,0xb67c393a,0x34a5b913,0xbb503a0f,0xbb0e3bf6,0x31792fd6,0xb78b2e46,0xbbe23bf1,0xb4a53913,0x3984b732,0xbba83a2f,0xb9cb3b25,
0x378bae46,0x3bcebaf6,0xbb0e3bf6,0xb30337e3,0x3addb9ed,0x38ecb984,0xb81d395f,0x3a4fb9cb,0x3beabb88,0x3732b848,0xb0b23564,0x3b25bac2,
0x3bc3bbfe,0x3444b5c2,0x33c6aa48,0x3bb6bb77,0x3a6dbb3b,0x2cb5b179,0x38c4b6d7,0x3bfabbe2,0xb9a839a8,0xba4f39cb,0x39a8b9a8,0xb8ec3984,
0xb9a839a8,0xbb253ac2,0x39a8b9a8,0xb7323848,0xb9a839a8,0xbbb63b77,0x39a8b9a8,0xb44435c2,0xb9a839a8,0xbbfa3be2,0x39a8b9a8,0xacb53179,
0x381db95f,0x3b50ba0f,0xbadd39ed,0x367cb93a,0x30b2b564,0x3be2bbf1,0xbbea3b88,0xb179afd6,0xb3c62a48,0x39cbbb25,0xbbc33bfe,0xb9843732,
0xb8c436d7,0x3303b7e3,0xba6d3b3b,0xbbce3af6,0xb4a53913,0xbbe23a4f,0x3ba8ba2f,0xb17938ec,0x378bae46,0xb9843b99,0x3b0ebbf6,0x39cbb505,
0x3ba8ba2f,0x33033444,0x34a5b913,0x3bcebbb6,0x3b0ebbf6,0x3b77b93a,0xb78b2e46,0x35c2ba0f,0x2a48b8c4,0x3bfaba8a,0xbbfe3a6d,0xacb5b89b,
0xbb3b381d,0x2fd6b9cb,0xb6d73add,0xbbf13984,0xb9ed3bea,0xbb993848,0x395fb0b2,0xb5053ac2,0x356433c6,0xb7e33b77,0x3b88bbc3,0x3af6b5c2,
0x323e3872,0xbb993ac2,0x3bd9baa7,0x35053848,0x3bd9baa7,0x37e335c2,0xb23eb872,0x3af6bb77,0xb23eb872,0x3a0fbbe2,0xbbd93aa7,0xb93ab179,
0xbbd93aa7,0xba4f2648,0x323e3872,0xb8ec3bff,0xb6d7b81d,0x3ac2baf6,0xbb3b3add,0xb848b7e3,0xb95f3bea,0xbb502cb5,0x39ed30b2,0xb67c3bfa,
0x3b88b3c6,0x31793a4f,0x3564bbc3,0x3be2b8ec,0xaa48ba6d,0x39cbbb99,0xbbfe38c4,0xb984b505,0x3913378b,0xb9843b25,0x3a2fbb0e,0x39cb3732,
0x2e46bba8,0x3bceb7e3,0xbbf634a5,0xb303baf6,0xba2f3b0e,0xbb77acb5,0x3913378b,0xb5c23bfa,0x3bf6b4a5,0x389b38ec,0x2e46bba8,0x3a8aba4f,
0xba6db6d7,0x37e3bb50,0xb8c43b3b,0xbaf6b67c,0x381d39ed,0xb93a3a8a,0x3addb95f,0x3a0f389b,0xb0b2bb88,0x3a4fb984,0xbbea3564,0xb8ecb9cb,
0xb3c63bfe,0xbb253848,0x3bc32a48,0x37323ac2,0x3b64361f,0xb4443b77,0x361fbb64,0x3bb635c2,0xbb64b61f,0x2cb5bbe2,0xb61f3b64,0xbbfab179,
0x3b64361f,0x2fd63bff,0x361fbb64,0x3bf1a648,0xbb64b61f,0xb505bbce,0xb61f3b64,0xbb993303,0xbbeab564,0x2648bb99,0xb0b23b88,0xbbffb505,
0x3bc3aa48,0x38483bb6,0xb3c6bbfe,0x3ac2b444,0xba6d36d7,0xbb50b93a,0x38c43b3b,0xb67c3a0f,0x381db9ed,0x3be22fd6,0xbaddb95f,0xb179bbf1,
0x3bf634a5,0x33033bb6,0xae46bba8,0x3bce3444,0xb913378b,0xbb77ba0f,0x3a2f3b0e,0xb5c2393a,0xae46bba8,0x3a8aafd6,0xbbf6b4a5,0xb89bbbf1,
0x3a2f3b0e,0x26483b25,0x3913b78b,0x3bff3732,0xbb88b3c6,0xb732bbce,0x35643bc3,0xbb25b303,0x2a48ba6d,0x3bb6367c,0xbbfeb8c4,0xb444bb50,
0x3b3b3add,0x2cb53a8a,0x36d7b81d,0x3bfa389b,0xb9ed30b2,0xbbf1b9cb,0x395f3bea,0xafd63984,0x3aa7323e,0x393a3be2,0xb872bbd9,0x3a0f3179,
0x38723bd9,0xb8ec2648,0x3aa7323e,0x3a4f3bff,0xbaa7b23e,0xbb25bbce,0x38723bd9,0xb7323303,0xb872bbd9,0x3444b67c,0xbaa7b23e,0xbbb6bb50,
0xb95fb0b2,0xba8abbf1,0x39ed3bea,0xb89bafd6,0xbb88bbc3,0x2648b732,0xb56433c6,0xbbffbb25,0xaa48b8c4,0x3ac237e3,0xbbfeba6d,0xb848baf6,
0x3b3b381d,0x3b503bfa,0xb6d7badd,0x367cacb5,0x378b2e46,0x3b773bfa,0xbb0ebbf6,0x35c22cb5,0x3ba83a2f,0x389b3a4f,0xb4a5b913,0x3a8a38ec,
0x3b0e3bf6,0x26483505,0x378b2e46,0x3bff3b99,0x34a53913,0xb848b444,0x3ba83a2f,0x3ac23bb6,0xb3c6aa48,0xbbf1bbff,0x3bc33bfe,0xafd6a648,
0xb8c4b6d7,0xbb99bbce,0x3a6d3b3b,0xb505b303,0xbaddb9ed,0xbaf6bb50,0x381d395f,0xb7e3b67c,0xbbeabb88,0xba0fba8a,0x30b23564,0xb93ab89b,
0x3c003c00,0xba4fb9cb,0,0xb8ecb984,0x3c003c00,0xbb25bac2,0,0xb732b848,0x3c003c00,0xbbb6bb77,0,0xb444b5c2,
0x3c003c00,0xbbfabbe2,0,0xacb5b179,0x33c62a48,0x367c393a,0x3bc33bfe,0xbb50ba0f,0x38c436d7,0xb1792fd6,0x3a6d3b3b,0xbbe2bbf1,
0x3add39ed,0xb984b732,0x381d395f,0xb9cbbb25,0x3bea3b88,0xbbcebaf6,0x30b23564,0xb303b7e3,0xbb0ebbf6,0x3be23a4f,0x378b2e46,0x317938ec,
0xb4a5b913,0x39843b99,0x3ba83a2f,0xb9cbb505,0x378b2e46,0xb3033444,0x3b0e3bf6,0xbbcebbb6,0x3ba83a2f,0xbb77b93a,0x34a53913,0xb5c2ba0f,
0xb95fb0b2,0x2cb5b89b,0xb9edbbea,0x3bfa3a8a,0xbb88bbc3,0x3bf13984,0x3564b3c6,0x2fd639cb,0xaa48b8c4,0x35053ac2,0x3bfe3a6d,0xbb99b848,
0x3b3b381d,0xbaf6b5c2,0x36d73add,0xb7e3bb77,0x38723bd9,0xbb99bac2,0xbaa7b23e,0x3505b848,0xbaa7b23e,0x37e3b5c2,0xb872bbd9,0x3af63b77,
0xb872bbd9,0x3a0f3be2,0x3aa7323e,0xb93a3179,0x3aa7323e,0xba4fa648,0x38723bd9,0xb8ecbbff,0x3b8833c6,0xb84837e3,0x35643bc3,0xbac2baf6,
0xaa483a6d,0xb67cbbfa,0xbbfeb8c4,0x3b502cb5,0xbb3bbadd,0x3be238ec,0x36d7b81d,0xb1793a4f,0x39edb0b2,0xb9843505,0x395f3bea,0xb9cbbb99,
0xae46bba8,0x39843b25,0x3bf634a5,0xb9cb3732,0x3a2f3b0e,0xbbceb7e3,0xb913378b,0x3303baf6,0xbbf6b4a5,0x3b77acb5,0xae46bba8,0x35c23bfa,
0x3913b78b,0xb89b38ec,0x3a2f3b0e,0xba8aba4f,0xbbeab564,0x3af6b67c,0x30b2bb88,0x37e33b50,0x3bc3aa48,0xba0f389b,0x33c63bfe,0xb93aba8a,
0xba6d36d7,0x38ecb9cb,0xb8c4bb3b,0x3a4f3984,0x381db9ed,0xb7323ac2,0x3add395f,0xbb25b848,0xb61f3b64,0xb444bb77,0xbb64b61f,0x3bb6b5c2,
0x361fbb64,0x2cb53be2,0x3b64361f,0xbbfa3179,0xb61f3b64,0x2fd6bbff,0xbb64b61f,0x3bf12648,0x361fbb64,0xb5053bce,0x3b64361f,0xbb99b303,
0x3a6d36d7,0xbbff3505,0xb8c43b3b,0xa648bb99,0xb81db9ed,0x3ac23444,0x3addb95f,0xb8483bb6,0x30b23b88,0xb67cba0f,0xbbea3564,0x3b50b93a,
0x33c6bbfe,0xb1793bf1,0x3bc32a48,0xbbe22fd6,0x3a2fbb0e,0xb3033bb6,0x3913378b,0xbbce3444,0xbbf634a5,0x3b77ba0f,0x2e46bba8,0x35c2393a,
0x3913378b,0xba8aafd6,0xba2f3b0e,0x389bbbf1,0x2e46bba8,0xa6483b25,0x3bf6b4a5,0xbbff3732,0xb6d7b81d,0x3b25b303,0x3b3bbadd,0xb7323bce,
0xb95f3bea,0x3444bb50,0xb9edb0b2,0x3bb6b67c,0x3b88b3c6,0xbbfa389b,0xb5643bc3,0x2cb5ba8a,0xaa48ba6d,0x2fd63984,0x3bfeb8c4,0xbbf139cb,
0xbbd93aa7,0x393abbe2,0xb23eb872,0x3a0fb179,0x323e3872,0xb8eca648,0xbbd93aa7,0x3a4fbbff,0x3bd9baa7,0xbb253bce,0x323e3872,0xb732b303,
0xb23eb872,0x3444367c,0x3bd9baa7,0xbbb63b50,0xaa4838c4,0xb89b2fd6,0xbbfe3a6d,0x3a8abbf1,0x3b3bb81d,0xbbff3b25,0xb6d73add,0xa648b732,
0x39edbbea,0xb8483af6,0x395fb0b2,0xbac237e3,0xb564b3c6,0x367c2cb5,0x3b88bbc3,0xbb503bfa,0x3ba8ba2f,0xbb773bfa,0xb4a53913,0xb5c22cb5,
0x3b0ebbf6,0xb89b3a4f,0x378bae46,0xba8a38ec,0x34a5b913,0xa6483505,0x3ba8ba2f,0xbbff3b99,0xb78b2e46,0x3848b444,0x3b0ebbf6,0xbac23bb6,
0x381db95f,0x2fd6a648,0x3addb9ed,0xbbf13bff,0x30b2b564,0x3505b303,0x3beabb88,0xbb993bce,0xb3c62a48,0x37e3b67c,0x3bc3bbfe,0xbaf63b50,
0xb8c436d7,0x393ab89b,0x3a6dbb3b,0xba0f3a8a,0xb9a839a8,0x3bf1bbff,0x39a8b9a8,0xafd62648,0xb9a839a8,0x3b99bbce,0x39a8b9a8,0xb5053303,
0xb9a839a8,0x3af6bb50,0x39a8b9a8,0xb7e3367c,0xb9a839a8,0x3a0fba8a,0x39a8b9a8,0xb93a389b,0xbadd39ed,0x35c2acb5,0xb81d395f,0x3b77bbfa,
0xbbea3b88,0x3a8ab8ec,0xb0b23564,0x389bba4f,0xbbc33bfe,0x3bffbb99,0x33c6aa48,0x2648b505,0xba6d3b3b,0x3ac2bbb6,0x38c4b6d7,0xb8483444,
0x34a5b913,0xba8a3bf1,0xbba83a2f,0x389bafd6,0xb78b2e46,0x26483732,0xbb0e3bf6,0x3bffbb25,0xbba83a2f,0x3ac2b7e3,0xb4a53913,0x3848baf6,
0xbb0e3bf6,0x3b50bbfa,0x378bae46,0xb67cacb5,0x3bfeba6d,0xba0f3179,0x2a48b8c4,0xb93a3be2,0x36d7badd,0xba4f3bff,0xbb3b381d,0x38ec2648,
0xb95f30b2,0x37323303,0xb9ed3bea,0x3b25bbce,0xbb883bc3,0x3bb6bb50,0x356433c6,0xb444b67c,0x323e3872,0x3732bbce,0x3bd9baa7,0xbb253303,
0x3bd9baa7,0xbbb6367c,0xb23eb872,0xb4443b50,0xb23eb872,0xacb53a8a,0xbbd93aa7,0x3bfab89b,0xbbd93aa7,0x3bf1b9cb,0x323e3872,0xafd6b984,
0xbb3b3add,0x3bceb444,0x36d7381d,0x3303bbb6,0x39ed30b2,0xb5c2b93a,0x395fbbea,0xbb773a0f,0x3564bbc3,0xb89b3bf1,0xbb8833c6,0x3a8a2fd6,
0xbbfe38c4,0x3bffb732,0x2a483a6d,0x2648bb25,0xb913b78b,0x26483b99,0xba2f3b0e,0x3bffb505,0xae463ba8,0x3848bbb6,0x3bf6b4a5,0xbac2b444,
0x3a2fbb0e,0xbb50393a,0xb913b78b,0x367c3a0f,0xbbf634a5,0x3be2afd6,0xae463ba8,0x3179bbf1,0x38c4bb3b,0xbbb635c2,0xba6db6d7,0x34443b77,
0xbadd395f,0x3bfab179,0x381d39ed,0xacb5bbe2,0x3beab564,0xbbf1a648,0xb0b2bb88,0xafd63bff,0xbbc3aa48,0x3b993303,0xb3c63bfe,0x3505bbce,
0x3b64361f,0xb7e3bb50,0x361fbb64,0xbaf6367c,0xbb64b61f,0x393a3a8a,0xb61f3b64,0x3a0fb89b,0x3b64361f,0xba4fb984,0x361fbb64,0xb8ec39cb,
0xbb64b61f,0x3b253848,0xb61f3b64,0x3732bac2,0xb0b23b88,0x39cbb732,0x3bea3564,0xb984bb25,0xb3c6bbfe,0xb3033af6,0xbbc32a48,0x3bce37e3,
0x38c43b3b,0xb5c2bbfa,0x3a6db6d7,0xbb772cb5,0xbaddb95f,0x3a8a3a4f,0xb81d39ed,0x389bb8ec,0xbbf6b4a5,0x3ac23af6,0x2e463ba8,0x3848b7e3,
0x3913b78b,0xbb50acb5,0xba2fbb0e,0x367c3bfa,0x2e463ba8,0x3179ba4f,0x3bf634a5,0xbbe2b8ec,0xba2fbb0e,0x39cb3b99,0xb913378b,0x3984b505,
0xb564bbc3,0xb5053848,0xbb88b3c6,0x3b993ac2,0x3bfe38c4,0xbaf6bb77,0x2a48ba6d,0xb7e335c2,0xb6d7381d,0x393ab179,0x3b3b3add,0xba0fbbe2,
0xb95fbbea,0x38ec3bff,0xb9ed30b2,0x3a4f2648,0x3aa7323e,0xbbfaba8a,0xb872bbd9,0xacb5389b,0x38723bd9,0xafd6b9cb,0x3aa7323e,0xbbf1b984,
0xbaa7b23e,0x3b993848,0x38723bd9,0xb505bac2,0xb872bbd9,0x37e33b77,0xbaa7b23e,0x3af635c2,0x39ed3bea,0xb179b8ec,0x395f30b2,0xbbe2ba4f,
0xb56433c6,0x39cb3505,0x3b883bc3,0xb984bb99,0xbbfeba6d,0x3bce3bb6,0x2a4838c4,0x3303b444,0xb6d7badd,0x35c23a0f,0xbb3bb81d,0x3b77393a,
0xb78bae46,0x3b503a0f,0x3b0e3bf6,0xb67cb93a,0xbba8ba2f,0x3be23bf1,0x34a53913,0x3179afd6,0xbb0ebbf6,0x39cb3b25,0xb78bae46,0x39843732,
0xb4a5b913,0x330337e3,0xbba8ba2f,0x3bce3af6,0xbbc3bbfe,0x38ec3984,0xb3c6aa48,0x3a4f39cb,0xba6dbb3b,0x37323848,0xb8c4b6d7,0x3b253ac2,
0xb81db95f,0x344435c2,0xbaddb9ed,0x3bb63b77,0xb0b2b564,0x2cb53179,0xbbeabb88,0x3bfa3be2,0x3c003c00,0x3a4f39cb,0,0x38ec3984,
0x3c003c00,0x3b253ac2,0,0x37323848,0x3c003c00,0x3bb63b77,0,0x344435c2,0x3c003c00,0x3bfa3be2,0,0x2cb53179,
0x33c62a48,0xb67cb93a,0x3bc33bfe,0x3b503a0f,0x38c436d7,0x3179afd6,0x3a6d3b3b,0x3be23bf1,0x3add39ed,0x39843732,0x381d395f,0x39cb3b25,
0x3bea3b88,0x3bce3af6,0x30b23564,0x330337e3,0xbb0ebbf6,0xbbe2ba4f,0x378b2e46,0xb179b8ec,0xb4a5b913,0xb984bb99,0x3ba83a2f,0x39cb3505,
0x378b2e46,0x3303b444,0x3b0e3bf6,0x3bce3bb6,0x3ba83a2f,0x3b77393a,0x34a53913,0x35c23a0f,0xb95fb0b2,0xacb5389b,0xb9edbbea,0xbbfaba8a,
0xbb88bbc3,0xbbf1b984,0x3564b3c6,0xafd6b9cb,0xaa48b8c4,0xb505bac2,0x3bfe3a6d,0x3b993848,0x3b3b381d,0x3af635c2,0x36d73add,0x37e33b77,
0x38723bd9,0x3b993ac2,0xbaa7b23e,0xb5053848,0xbaa7b23e,0xb7e335c2,0xb872bbd9,0xbaf6bb77,0xb872bbd9,0xba0fbbe2,0x3aa7323e,0x393ab179,
0x3aa7323e,0x3a4f2648,0x38723bd9,0x38ec3bff,0x3b8833c6,0x3848b7e3,0x35643bc3,0x3ac23af6,0xaa483a6d,0x367c3bfa,0xbbfeb8c4,0xbb50acb5,
0xbb3bbadd,0xbbe2b8ec,0x36d7b81d,0x3179ba4f,0x39edb0b2,0x3984b505,0x395f3bea,0x39cb3b99,0xae46bba8,0xb984bb25,0x3bf634a5,0x39cbb732,
0x3a2f3b0e,0x3bce37e3,0xb913378b,0xb3033af6,0xbbf6b4a5,0xbb772cb5,0xae46bba8,0xb5c2bbfa,0x3913b78b,0x389bb8ec,0x3a2f3b0e,0x3a8a3a4f,
0xbbeab564,0xbaf6367c,0x30b2bb88,0xb7e3bb50,0x3bc3aa48,0x3a0fb89b,0x33c63bfe,0x393a3a8a,0xba6d36d7,0xb8ec39cb,0xb8c4bb3b,0xba4fb984,
0x381db9ed,0x3732bac2,0x3add395f,0x3b253848,0xb61f3b64,0x34443b77,0xbb64b61f,0xbbb635c2,0x361fbb64,0xacb5bbe2,0x3b64361f,0x3bfab179,
0xb61f3b64,0xafd63bff,0xbb64b61f,0xbbf1a648,0x361fbb64,0x3505bbce,0x3b64361f,0x3b993303,0x3a6d36d7,0x3bffb505,0xb8c43b3b,0x26483b99,
0xb81db9ed,0xbac2b444,0x3addb95f,0x3848bbb6,0x30b23b88,0x367c3a0f,0xbbea3564,0xbb50393a,0x33c6bbfe,0x3179bbf1,0x3bc32a48,0x3be2afd6,
0x3a2fbb0e,0x3303bbb6,0x3913378b,0x3bceb444,0xbbf634a5,0xbb773a0f,0x2e46bba8,0xb5c2b93a,0x3913378b,0x3a8a2fd6,0xba2f3b0e,0xb89b3bf1,
0x2e46bba8,0x2648bb25,0x3bf6b4a5,0x3bffb732,0xb6d7b81d,0xbb253303,0x3b3bbadd,0x3732bbce,0xb95f3bea,0xb4443b50,0xb9edb0b2,0xbbb6367c,
0x3b88b3c6,0x3bfab89b,0xb5643bc3,0xacb53a8a,0xaa48ba6d,0xafd6b984,0x3bfeb8c4,0x3bf1b9cb,0xbbd93aa7,0xb93a3be2,0xb23eb872,0xba0f3179,
0x323e3872,0x38ec2648,0xbbd93aa7,0xba4f3bff,0x3bd9baa7,0x3b25bbce,0x323e3872,0x37323303,0xb23eb872,0xb444b67c,0x3bd9baa7,0x3bb6bb50,
0xaa4838c4,0x389bafd6,0xbbfe3a6d,0xba8a3bf1,0x3b3bb81d,0x3bffbb25,0xb6d73add,0x26483732,0x39edbbea,0x3848baf6,0x395fb0b2,0x3ac2b7e3,
0xb564b3c6,0xb67cacb5,0x3b88bbc3,0x3b50bbfa,0x3ba8ba2f,0x3b77bbfa,0xb4a53913,0x35c2acb5,0x3b0ebbf6,0x389bba4f,0x378bae46,0x3a8ab8ec,
0x34a5b913,0x2648b505,0x3ba8ba2f,0x3bffbb99,0xb78b2e46,0xb8483444,0x3b0ebbf6,0x3ac2bbb6,0x381db95f,0xafd62648,0x3addb9ed,0x3bf1bbff,
0x30b2b564,0xb5053303,0x3beabb88,0x3b99bbce,0xb3c62a48,0xb7e3367c,0x3bc3bbfe,0x3af6bb50,0xb8c436d7,0xb93a389b,0x3a6dbb3b,0x3a0fba8a,
0xb9a839a8,0xbbf13bff,0x39a8b9a8,0x2fd6a648,0xb9a839a8,0xbb993bce,0x39a8b9a8,0x3505b303,0xb9a839a8,0xbaf63b50,0x39a8b9a8,0x37e3b67c,
0xb9a839a8,0xba0f3a8a,0x39a8b9a8,0x393ab89b,0xbadd39ed,0xb5c22cb5,0xb81d395f,0xbb773bfa,0xbbea3b88,0xba8a38ec,0xb0b23564,0xb89b3a4f,
0xbbc33bfe,0xbbff3b99,0x33c6aa48,0xa6483505,0xba6d3b3b,0xbac23bb6,0x38c4b6d7,0x3848b444,0x34a5b913,0x3a8abbf1,0xbba83a2f,0xb89b2fd6,
0xb78b2e46,0xa648b732,0xbb0e3bf6,0xbbff3b25,0xbba83a2f,0xbac237e3,0xb4a53913,0xb8483af6,0xbb0e3bf6,0xbb503bfa,0x378bae46,0x367c2cb5,
0x3bfeba6d,0x3a0fb179,0x2a48b8c4,0x393abbe2,0x36d7badd,0x3a4fbbff,0xbb3b381d,0xb8eca648,0xb95f30b2,0xb732b303,0xb9ed3bea,0xbb253bce,
0xbb883bc3,0xbbb63b50,0x356433c6,0x3444367c,0x323e3872,0xb7323bce,0x3bd9baa7,0x3b25b303,0x3bd9baa7,0x3bb6b67c,0xb23eb872,0x3444bb50,
0xb23eb872,0x2cb5ba8a,0xbbd93aa7,0xbbfa389b,0xbbd93aa7,0xbbf139cb,0x323e3872,0x2fd63984,0xbb3b3add,0xbbce3444,0x36d7381d,0xb3033bb6,
0x39ed30b2,0x35c2393a,0x395fbbea,0x3b77ba0f,0x3564bbc3,0x389bbbf1,0xbb8833c6,0xba8aafd6,0xbbfe38c4,0xbbff3732,0x2a483a6d,0xa6483b25,
0xb913b78b,0xa648bb99,0xba2f3b0e,0xbbff3505,0xae463ba8,0xb8483bb6,0x3bf6b4a5,0x3ac23444,0x3a2fbb0e,0x3b50b93a,0xb913b78b,0xb67cba0f,
0xbbf634a5,0xbbe22fd6,0xae463ba8,0xb1793bf1,0x38c4bb3b,0x3bb6b5c2,0xba6db6d7,0xb444bb77,0xbadd395f,0xbbfa3179,0x381d39ed,0x2cb53be2,
0x3beab564,0x3bf12648,0xb0b2bb88,0x2fd6bbff,0xbbc3aa48,0xbb99b303,0xb3c63bfe,0xb5053bce,0x3b64361f,0x37e33b50,0x361fbb64,0x3af6b67c,
0xbb64b61f,0xb93aba8a,0xb61f3b64,0xba0f389b,0x3b64361f,0x3a4f3984,0x361fbb64,0x38ecb9cb,0xbb64b61f,0xbb25b848,0xb61f3b64,0xb7323ac2,
0xb0b23b88,0xb9cb3732,0x3bea3564,0x39843b25,0xb3c6bbfe,0x3303baf6,0xbbc32a48,0xbbceb7e3,0x38c43b3b,0x35c23bfa,0x3a6db6d7,0x3b77acb5,
0xbaddb95f,0xba8aba4f,0xb81d39ed,0xb89b38ec,0xbbf6b4a5,0xbac2baf6,0x2e463ba8,0xb84837e3,0x3913b78b,0x3b502cb5,0xba2fbb0e,0xb67cbbfa,
0x2e463ba8,0xb1793a4f,0x3bf634a5,0x3be238ec,0xba2fbb0e,0xb9cbbb99,0xb913378b,0xb9843505,0xb564bbc3,0x3505b848,0xbb88b3c6,0xbb99bac2,
0x3bfe38c4,0x3af63b77,0x2a48ba6d,0x37e3b5c2,0xb6d7381d,0xb93a3179,0x3b3b3add,0x3a0f3be2,0xb95fbbea,0xb8ecbbff,0xb9ed30b2,0xba4fa648,
0x3aa7323e,0x3bfa3a8a,0xb872bbd9,0x2cb5b89b,0x38723bd9,0x2fd639cb,0x3aa7323e,0x3bf13984,0xbaa7b23e,0xbb99b848,0x38723bd9,0x35053ac2,
0xb872bbd9,0xb7e3bb77,0xbaa7b23e,0xbaf6b5c2,0x39ed3bea,0x317938ec,0x395f30b2,0x3be23a4f,0xb56433c6,0xb9cbb505,0x3b883bc3,0x39843b99,
0xbbfeba6d,0xbbcebbb6,0x2a4838c4,0xb3033444,0xb6d7badd,0xb5c2ba0f,0xbb3bb81d,0xbb77b93a,0xb78bae46,0xbb50ba0f,0x3b0e3bf6,0x367c393a,
0xbba8ba2f,0xbbe2bbf1,0x34a53913,0xb1792fd6,0xbb0ebbf6,0xb9cbbb25,0xb78bae46,0xb984b732,0xb4a5b913,0xb303b7e3,0xbba8ba2f,0xbbcebaf6,
0xbbc3bbfe,0xb8ecb984,0xb3c6aa48,0xba4fb9cb,0xba6dbb3b,0xb732b848,0xb8c4b6d7,0xbb25bac2,0xb81db95f,0xb444b5c2,0xbaddb9ed,0xbbb6bb77,
0xb0b2b564,0xacb5b179,0xbbeabb88,0xbbfabbe2,0x3c003c00,0x96480000,0x3c003c00,0xa311a248,0x3c003c00,0x9cb69a48,0x3c003c00,0xa452a3db,
0x3c003c00,0x9fdb9e48,0x3c003c00,0xa51ba4b6,0x3c003c00,0xa17fa0b6,0x3bff3c00,0xa5e4a57f,0x3c003c00,0x9fdb0000,0x3bfb3bfc,0xac6aabd9,
0x3bff3c00,0xa5e4a3db,0x3bf93bfa,0xad65ace7,0x3bfe3bff,0xa8e8a7da,0x3bf63bf7,0xae5fade2,0x3bfd3bfe,0xaadea9e3,0x3bf23bf4,0xaf59aedc,
0x3c003c00,0xa3110000,0x3bf03bf4,0xafefaf0e,0x3bfe3bff,0xa94da711,0x3be83bed,0xb0d7b067,0x3bfb3bfd,0xac6aab11,0x3bdf3be4,0xb1b6b147,
0x3bf63bf9,0xae2dad4c,0x3bd43bda,0xb294b226,0x3c003c00,0xa51b0000,0x3bdf3be6,0xb1b6b115,0x3bfc3bfe,0xaba7a91b,0x3bcf3bd7,0xb2f7b257,
0x3bf63bf9,0xae5fad1a,0x3bbc3bc6,0xb41ab396,0x3bec3bf1,0xb074afa4,0x3ba53bb1,0xb4b7b469,0x3bff3c00,0xa6ad0000,0x3bc83bd4,0xb371b2a1,
0x3bfa3bfd,0xad00aaac,0x3bac3bbb,0xb487b420,0x3bef3bf5,0xb029aeaa,0x3b8b3b9d,0xb552b4ed,0x3bde3be7,0xb1cfb0fd,0x3b653b79,0xb61ab5b6,
0x3bff3c00,0xa81f0000,0x3bab3bbc,0xb493b414,0x3bf63bfc,0xae2dac1f,0x3b813b97,0xb58db511,0x3be53bef,0xb122b01d,0x3b4f3b69,0xb682b608,
0x3bcc3bda,0xb328b226,0x3b163b33,0xb76fb6f9,0x3bfe3c00,0xa8e80000,0x3b873ba0,0xb56ab4d5,0x3bf23bfa,0xaf59ace7,0x3b4c3b6b,0xb68db5fd,
0x3bda3be8,0xb219b0e4,0x3b073b2b,0xb7a6b71b,0x3bb73bca,0xb43eb34c,0x3ab63ae0,0xb85ab817,0x3bfe3c00,0xa9b10000,0x3b5e3b80,0xb63cb593,
0x3bee3bf8,0xb042adb0,0x3b103b39,0xb785b6e3,0x3bce3be0,0xb30fb1aa,0x3ab33ae3,0xb85fb812,0x3b9e3bb7,0xb4e7b438,0x3a493a7f,0xb8f3b8ab,
0x3bfd3c00,0xaa7a0000,0x3b2f3b5a,0xb70ab64e,0x3be83bf6,0xb0d7ae78,0x3acb3aff,0xb83ab7c2,0x3bbf3bd6,0xb402b26f,0x3a543a92,0xb8e5b891,
0x3b813ba2,0xb58db4c9,0x39cd3a13,0xb982b935,0x3bfd3c00,0xab430000,0x3afb3b30,0xb7d2b705,0x3be23bf3,0xb16caf40,0x3a7e3abf,0xb8adb84d,
0x3bae3bcb,0xb47bb334,0x39eb3a37,0xb962b909,0x3b603b8a,0xb631b558,0x3946399b,0xba04b9b5,0x3bfc3c00,0xac060000,0x3ac13b02,0xb84ab7b7,
0x3bdc3bf0,0xb201b004,0x3a293a78,0xb91bb8b5,0x3b9c3bc0,0xb4f3b3f7,0x397939d4,0xb9d6b97b,0x3b3d3b70,0xb6d2b5e5,0x38b23918,0xba7aba2b,
0x3bfb3c00,0xac6a0000,0x3a813ad0,0xb8a8b832,0x3bd43bed,0xb294b067,0x39cd3a2b,0xb982b918,0x3b873bb2,0xb56ab45d,0x38fd3969,0xba41b9e5,
0x3b163b53,0xb76fb670,0x3815388c,0xbae1ba95,0x3bfa3c00,0xacce0000,0x3a3d3a99,0xb902b887,0x3bcc3be9,0xb328b0cb,0x396b39d8,0xb9e3b976,
0x3b713ba4,0xb5dfb4bd,0x387a38f6,0xbaa2ba47,0x3aeb3b33,0xb805b6f9,0x36dd37ee,0xbb3abaf3,0x3bf93c00,0xad330000,0x39f43a5e,0xb958b8d8,
0x3bc33be5,0xb3bab12e,0x39023980,0xba3db9d0,0x3b593b95,0xb654b51d,0x37dd387c,0xbaf7baa0,0x3abd3b11,0xb850b780,0x358136b5,0xbb83bb43,
0x3bf83c00,0xad970000,0x39a63a1f,0xb9aab927,0x3bba3be1,0xb426b191,0x38943922,0xba90ba23,0x3b3f3b84,0xb6c6b57c,0x36bb37f9,0xbb42baf0,
0x3a8c3aed,0xb899b802,0x341a3570,0xbbbcbb86,0x3bf73c00,0xadfb0000,0x395439dc,0xb9f8b972,0x3bb03bdc,0xb46fb1f4,0x382038bf,0xbadbba71,
0x3b243b72,0xb737b5da,0x358d36ee,0xbb81bb36,0x3a583ac6,0xb8e0b842,0x31533420,0xbbe3bbbb,0x3bf63c00,0xae5f0000,0x38fd3996,0xba41b9ba,
0x3ba53bd7,0xb4b7b257,0x374e3858,0xbb1ebab8,0x3b073b5f,0xb7a6b637,0x345735da,0xbbb3bb72,0x3a213a9c,0xb924b881,0x2cce3191,0xbbfabbe1,
0x3bf53c00,0xaec30000,0x38a3394d,0xba85b9fe,0x3b9a3bd2,0xb4ffb2b9,0x365437d8,0xbb59baf9,0x3ae83b4b,0xb80ab693,0x323234bd,0xbbd9bba4,
0x39e73a71,0xb966b8bf,0xa4522db0,0xbc00bbf8,0x3bf33c00,0xaf270000,0x38453900,0xbac4ba3f,0x3b8e3bcd,0xb546b31b,0x355236f9,0xbb8bbb33,
0x3ac73b36,0xb840b6ee,0x2f593334,0xbbf2bbcb,0x39aa3a43,0xb9a6b8fb,0xaef51a48,0xbbf4bc00,0x3bf23c00,0xaf8b0000,0x37c838b0,0xbafeba7c,
0x3b813bc7,0xb58db37d,0x344b3614,0xbbb5bb67,0x3aa53b20,0xb874b748,0x288430e4,0xbbffbbe8,0x396b3a13,0xb9e3b935,0xb263ad4c,0xbbd7bbf9,
0x3bf03c00,0xafef0000,0x36ff385d,0xbb32bab5,0x3b733bc1,0xb5d4b3df,0x327c3529,0xbbd6bb93,0x3a813b08,0xb8a8b7a1,0xa9b12d1a,0xbbfebbf9,
0x392939e1,0xba1db96d,0xb49fb160,0xbba9bbe3,0x3bef3c00,0xb0290000,0x36313807,0xbb60bae9,0x3b653bbb,0xb61ab420,0x305b3438,0xbbedbbb7,
0x3a5c3af0,0xb8dbb7f9,0xafef1e48,0xbbf0bc00,0x38e539ad,0xba54b9a4,0xb602b408,0xbb6abbbe,0x3bed3c00,0xb05b0000,0x355e375e,0xbb89bb1a,
0x3b573bb4,0xb65fb451,0x2c6a3288,0xbbfbbbd5,0x3a353ad6,0xb90cb828,0xb27cac51,0xbbd6bbfb,0x389e3976,0xba89b9d8,0xb759b558,0xbb1bbb8a,
0x3beb3c00,0xb08d0000,0x348736aa,0xbbacbb46,0x3b473bad,0xb6a4b481,0x16483099,0xbc00bbeb,0x3a0d3abc,0xb93cb852,0xb47bb080,0xbbaebbec,
0x3855393e,0xbababa0b,0xb850b69e,0xbabdbb49,0x3be93c00,0xb0be0000,0x335935f1,0xbbc9bb6e,0x3b373ba6,0xb6e8b4b1,0xac382d4c,0xbbfcbbf9,
0x39e33aa0,0xb96bb87c,0xb5b1b2d2,0xbb7abbd1,0x380a3905,0xbae8ba3b,0xb8eab7d8,0xba50baf9,0x3be73c00,0xb0f00000,0x319e3534,0xbbe0bb91,
0x3b273b9e,0xb72cb4e1,0xb042257f,0xbbeebc00,0x39b83a83,0xb999b8a6,0xb6ddb48d,0xbb3abbab,0x377a38c9,0xbb13ba69,0xb979b881,0xb9d6ba9c,
0x3be53c00,0xb1220000,0x2fbd3475,0xbbf1bbaf,0x3b163b97,0xb76fb511,0xb263a91b,0xbbd7bbfe,0x398b3a65,0xb9c5b8ce,0xb7feb5ab,0xbaeebb7b,
0x36dd388c,0xbb3aba95,0xb9fcb90e,0xb94fba33,0x3be33c00,0xb1530000,0x2c383365,0xbbfcbbc9,0x3b043b8f,0xb7b2b540,0xb43eae78,0xbbb7bbf6,
0x395d3a47,0xb9f0b8f6,0xb889b6c1,0xba97bb41,0x363c384d,0xbb5ebabf,0xba73b992,0xb8bcb9be,0x3be13c00,0xb1850000,0x217f31db,0xbc00bbdd,
0x3af13b86,0xb7f3b570,0xb546b12e,0xbb8ebbe5,0x392e3a27,0xba19b91d,0xb90cb7cd,0xba35bafc,0x3599380d,0xbb7fbae6,0xbadbba0b,0xb820b93e,
0x3bdf3c00,0xb1b60000,0xa9b1304e,0xbbfebbed,0x3ade3b7d,0xb81ab59f,0xb648b31b,0xbb5cbbcd,0x38fd3a07,0xba41b943,0xb986b867,0xb9c9baae,
0x34f33796,0xbb9cbb0b,0xbb35ba78,0xb6f4b8b5,0x3bdd3c00,0xb1e80000,0xae5f2d7e,0xbbf6bbf8,0x3acb3b74,0xb83ab5ce,0xb742b481,0xbb21bbad,
0x38cc39e5,0xba67b969,0xb9f8b8e2,0xb954ba56,0x344b3710,0xbbb5bb2e,0xbb7fbad9,0xb599b822,0x3bda3c00,0xb2190000,0xb0f028b6,0xbbe7bbff,
0x3ab63b6b,0xb85ab5fd,0xb81ab570,0xbadebb86,0x389939c3,0xba8cb98d,0xba60b956,0xb8d6b9f6,0x33403687,0xbbcbbb4e,0xbbb8bb2e,0xb432b710,
0x3bff3bff,0xa6ada648,0x3bfe3bff,0xa8e8a8b6,0x3bff3bff,0xa776a711,0x3bfe3bfe,0xa94da91b,0x3bff3bff,0xa81fa7da,0x3bfe3bfe,0xa9b1a97f,
0x3bff3bff,0xa884a852,0x3bfe3bfe,0xaa16a9e3,0x3bef3bf1,0xb029afd6,0x3bda3bdd,0xb219b1db,0x3bea3bed,0xb0a6b067,0x3bd43bd7,0xb294b257,
0x3be53be8,0xb122b0e4,0x3bce3bd1,0xb30fb2d2,0x3be03be3,0xb19eb160,0x3bc63bca,0xb389b34c,0x3bc83bce,0xb371b303,0x3b873b91,0xb56ab534,
0x3bba3bc1,0xb426b3df,0x3b733b7d,0xb5d4b59f,0x3bab3bb2,0xb493b45d,0x3b5e3b69,0xb63cb608,0x3b9a3ba2,0xb4ffb4c9,0x3b473b53,0xb6a4b670,
0x3b8b3b99,0xb552b505,0x3b073b1a,0xb7a6b75e,0x3b6f3b7d,0xb5ebb59f,0x3ade3af3,0xb81ab7ee,0x3b4f3b5f,0xb682b637,0x3ab33ac9,0xb85fb83d,
0x3b2c3b3e,0xb715b6cc,0x3a853a9c,0xb8a3b881,0x3b3a3b50,0xb6ddb67c,0x3a5c3a7c,0xb8dbb8b0,0x3b0a3b22,0xb79bb73d,0x3a193a3b,0xb92eb905,
0x3ad53af0,0xb82ab7f9,0x39d239f6,0xb97db956,0x3a9b3ab8,0xb884b858,0x398639ad,0xb9c9b9a4,0x3ad53af6,0xb82ab7e3,0x398b39ba,0xb9c5b996,
0x3a8c3ab1,0xb899b862,0x3929395b,0xba1db9f2,0x3a3d3a65,0xb902b8ce,0x38c138f6,0xba6fba47,0x39e73a13,0xb966b935,0x3855388c,0xbababa95,
0x3a5c3a8a,0xb8dbb89b,0x389938d8,0xba8cba5e,0x39f83a2b,0xb954b918,0x38153858,0xbae1bab8,0x398b39c3,0xb9c5b98d,0x371537a1,0xbb2cbb08,
0x39163951,0xba2db9fa,0x35f73687,0xbb6cbb4e,0x39d23a0f,0xb97db93a,0x371537b7,0xbb2cbb02,0x394f3992,0xb9fcb9be,0x35c83670,0xbb76bb53,
0x38c13909,0xba6fba37,0x346f351d,0xbbb0bb95,0x382a3877,0xbad5baa3,0x3219337d,0xbbdabbc7,0x39373984,0xba11b9cb,0x34cf3593,0xbba1bb80,
0x389438e7,0xba90ba52,0x327c3408,0xbbd6bbbe,0x37c8383d,0xbafebac9,0x2e9130e4,0xbbf5bbe8,0x36543710,0xbb59bb2e,0x16482aac,0xbc00bbfd,
0x388e38ec,0xba93ba4f,0x30d732a1,0xbbe8bbd4,0x3790382d,0xbb0dbad3,0x28e82e14,0xbbfebbf7,0x35eb36c1,0xbb6fbb41,0xaccea4b6,0xbbfabc00,
0x34323511,0xbbb8bb97,0xb201b036,0xbbdcbbee,0x37b23848,0xbb04bac2,0x96482bd9,0xbc00bbfc,0x35df36cc,0xbb71bb3e,0xb010ac1f,0xbbefbbfc,
0x33eb34ed,0xbbc0bb9d,0xb402b20d,0xbbbfbbdb,0x2fef31f4,0xbbf0bbdc,0xb5ebb4f9,0xbb6fbb9b,0x36313732,0xbb60bb25,0xb0f0ad7e,0xbbe7bbf8,
0x341a3529,0xbbbcbb93,0xb49fb31b,0xbba9bbcd,0x2fbd320d,0xbbf1bbdb,0xb6afb5ab,0xbb45bb7b,0xa4522aac,0xbc00bbfd,0xb850b7ac,0xbabdbb05,
0x349f35c2,0xbba9bb77,0xb4dbb365,0xbb9fbbc9,0x308d32ea,0xbbebbbd0,0xb715b5fd,0xbb2cbb6b,0x9fdb2c51,0xbc00bbfb,0xb894b812,0xba90bae3,
0xb109ad4c,0xbbe6bbf9,0xb982b90e,0xb9cdba33,0x32013444,0xbbdcbbb6,0xb721b5f1,0xbb2abb6e,0x26ad2edc,0xbbffbbf4,0xb8adb822,0xba7ebad9,
0xb05bab11,0xbbedbbfd,0xb9aab930,0xb9a6ba17,0xb4b7b2ea,0xbba5bbd0,0xba81ba1b,0xb8a8b92b,0x2d653179,0xbbf9bbe2,0xb89eb807,0xba89bae9,
0xadc99a48,0xbbf8bc00,0xb9afb92b,0xb9a1ba1b,0xb432b1aa,0xbbb8bbe0,0xba93ba27,0xb88eb91d,0xb6d2b587,0xbb3dbb82,0xbb45baf3,0xb6afb7ee,
0xa51b2cb5,0xbc00bbfa,0xb990b900,0xb9c0ba3f,0xb294af40,0xbbd4bbf3,0xba89ba13,0xb89eb935,0xb625b4bd,0xbb63bba4,0xbb47baf0,0xb6a4b7f9,
0xb865b780,0xbab0bb11,0xbbc5bb8f,0xb3a2b540,0xafefa648,0xbbf0bbff,0xba60b9dc,0xb8d6b972,0xb517b31b,0xbb96bbcd,0xbb35bad3,0xb6f4b82d,
0xb7feb693,0xbaeebb4b,0xbbc0bb84,0xb3ebb57c,0xb94ab8ab,0xba00ba7f,0xbbfdbbe9,0xaa7ab0cb,0xb340afd6,0xbbcbbbf1,0xbb0aba99,0xb79bb887,
0xb6d2b540,0xbb3dbb8f,0xbbaebb67,0xb47bb614,0xb8dbb828,0xba5cbad6,0xbbfbbbe0,0xac9cb1aa,0xba15b980,0xb933b9d0,0xbbecbbff,0x30742852,
0xb53ab303,0xbb90bbce,0xbb89bb30,0xb55eb705,0xb83ab6e3,0xbacbbb39,0xbbf2bbca,0xaf8bb34c,0xb9a1b8f6,0xb9afba47,0xbbf5bc00,0x2ec39e48,
0xbac1ba3b,0xb84ab905,0xbb92bbd0,0x352f32ea,0xb6c6b505,0xbb3fbb99,0xbbdcbba0,0xb201b4d5,0xb8fdb838,0xba41bacc,0xbbfebbfb,0x2a16ac83,
0xba50b9b1,0xb8eab99f,0xbbaebbe4,0x347b3147,0xbb4abad9,0xb699b822,0xbaf1bb5d,0x37f33642,0xb820b67c,0xbadbbb50,0xbbffbbe6,0xa884b115,
0xb9afb8f1,0xb9a1ba4b,0xbbd2bbf8,0x32c62db0,0xbae5ba56,0xb80fb8e2,0xbb2abb8c,0x3721354c,0xbbaebb58,0xb47bb659,0xba11baaa,0x3937386d,
0xb8d1b7e3,0xba64baf6,0xbbf2bc00,0x2f8ba248,0xba4db99b,0xb8eeb9b5,0xbb6fbbc1,0x35eb33df,0xbb5cbae3,0xb648b812,0xba6bbafc,0x38c737cd,
0xbbebbbb4,0xb08db451,0xb8f8b9be,0x3a453992,0xb974b89b,0xb9daba8a,0xbbb5bbed,0x344b304e,0xbad5ba33,0xb82ab90e,0xbad8bb58,0x38253659,
0xbbb3bb55,0xb457b665,0xb979ba37,0x39d63909,0xbc00bbed,0x9648b067,0xb764b8a0,0x3b183a87,0xba09b93a,0xb941ba0f,0xbb4abbaf,0x36993475,
0xbb45bab8,0xb6afb858,0xba11babf,0x3937384d,0xbbeabbab,0xb0a6b48d,0xb85ab943,0x3ab63a07,0xbbecbc00,0x30749a48,0xb493b6b5,0x3bab3b43,
0xba8cb9cb,0xb899b984,0xbab3bb46,0x385f36aa,0xbb9cbb28,0xb4f3b726,0xb91fb9fa,0x3a253951,0xbc00bbe4,0xa452b147,0xb631b828,0x3b603ad6,
0xbbb0bbee,0x346f3036,0xae5fb3df,0x3bf63bc1,0xbafeba4f,0xb7c8b8ec,0xb9f4bab5,0x3958385d,0xbbd8bb82,0xb24bb587,0xb80ab90e,0x3ae83a33,
0xbbf3bbfe,0x2f27a97f,0xb2f7b5da,0x3bcf3b72,0xbb4cbbb7,0x368d3438,0x2dc9ac1f,0x3bf83bfc,0xbb5cbac2,0xb648b848,0xb911b9fe,0x3a31394d,
0xbbf9bbc4,0xad33b3ae,0xb5b1b802,0x3b7a3aed,0xbbc5bbf9,0x33a22d1a,0xa94db26f,0x3bfe3bd6,0xbac4bb5d,0x38453642,0x346f2fa4,0x3bb03bf1,
0xbba5bb25,0xb4b7b732,0xb80fb927,0x3ae53a1f,0xbbffbbee,0x2884b036,0xb24bb5b6,0x3bd83b79,0xbb76bbd6,0x35c8326f,0x305ba7da,0x3bed3bff,
0xba19bae0,0x392e3817,0x374234c9,0x3b213ba2,0xbbd9bb77,0xb232b5c2,0xb5ebb832,0x3b6f3ad0,0xbbe8bc00,0x30d7a57f,0xa81fb288,0x3bff3bd5,
0xbb07bb95,0x37a6351d,0x34f33080,0x3b9c3bec,0xb94fba43,0x39fc38fb,0x38ea3780,0x3a503b11,0xbbf8bbb6,0xadc9b444,0xb328b64e,0x3bcc3b5a,
0xbbb7bbf8,0x343e2db0,0x3042a9e3,0x3bee3bfe,0xba7abb36,0x38b236ee,0x379034ed,0x3b0d3b9d,0xb86ab989,0x3aac39c7,0x3a0438fb,0x39463a43,
0xbc00bbe2,0x2311b179,0xac9cb414,0x3bfb3bbc,0xbb6abbd7,0x36023257,0x34b72f40,0x3ba53bf3,0xb9d2babc,0x397d3852,0x38f83775,0x3a453b14,
0xb6ddb8b5,0x3b3a3a78,0x3ae83a0b,0x380a393e,0xbbf2bbfa,0x2f8bacb5,0x2d33af0e,0x3bf93bf4,0xbb04bb9e,0x37b234e1,0x372c3451,0x3b273bb4,
0xb911ba27,0x3a31391d,0x3a0038e2,0x394a3a56,0xb4c3b796,0x3ba33b0b,0x3b8b3ae6,0x3552380d,0x4c004c00,0x26480000,0x4c004c00,0x33113248,
0x4c004c00,0x2cb62a48,0x4c004c00,0x345233db,0x4c004c00,0x2fdb2e48,0x4c004c00,0x351b34b6,0x4c004c00,0x317f30b6,0x4bff4c00,0x35e4357f,
0x4c004c00,0x2fdb0000,0x4bfb4bfc,0x3c6a3bd9,0x4bff4c00,0x35e433db,0x4bf94bfa,0x3d653ce7,0x4bfe4bff,0x38e837da,0x4bf64bf7,0x3e5f3de2,
0x4bfd4bfe,0x3ade39e3,0x4bf24bf4,0x3f593edc,0x4c004c00,0x33110000,0x4bf04bf4,0x3fef3f0e,0x4bfe4bff,0x394d3711,0x4be84bed,0x40d74067,
0x4bfb4bfd,0x3c6a3b11,0x4bdf4be4,0x41b64147,0x4bf64bf9,0x3e2d3d4c,0x4bd44bda,0x42944226,0x4c004c00,0x351b0000,0x4bdf4be6,0x41b64115,
0x4bfc4bfe,0x3ba7391b,0x4bcf4bd7,0x42f74257,0x4bf64bf9,0x3e5f3d1a,0x4bbc4bc6,0x441a4396,0x4bec4bf1,0x40743fa4,0x4ba54bb1,0x44b74469,
0x4bff4c00,0x36ad0000,0x4bc84bd4,0x437142a1,0x4bfa4bfd,0x3d003aac,0x4bac4bbb,0x44874420,0x4bef4bf5,0x40293eaa,0x4b8b4b9d,0x455244ed,
0x4bde4be7,0x41cf40fd,0x4b654b79,0x461a45b6,0x4bff4c00,0x381f0000,0x4bab4bbc,0x44934414,0x4bf64bfc,0x3e2d3c1f,0x4b814b97,0x458d4511,
0x4be54bef,0x4122401d,0x4b4f4b69,0x46824608,0x4bcc4bda,0x43284226,0x4b164b33,0x476f46f9,0x4bfe4c00,0x38e80000,0x4b874ba0,0x456a44d5,
0x4bf24bfa,0x3f593ce7,0x4b4c4b6b,0x468d45fd,0x4bda4be8,0x421940e4,0x4b074b2b,0x47a6471b,0x4bb74bca,0x443e434c,0x4ab64ae0,0x485a4817,
0x4bfe4c00,0x39b10000,0x4b5e4b80,0x463c4593,0x4bee4bf8,0x40423db0,0x4b104b39,0x478546e3,0x4bce4be0,0x430f41aa,0x4ab34ae3,0x485f4812,
0x4b9e4bb7,0x44e74438,0x4a494a7f,0x48f348ab,0x4bfd4c00,0x3a7a0000,0x4b2f4b5a,0x470a464e,0x4be84bf6,0x40d73e78,0x4acb4aff,0x483a47c2,
0x4bbf4bd6,0x4402426f,0x4a544a92,0x48e54891,0x4b814ba2,0x458d44c9,0x49cd4a13,0x49824935,0x4bfd4c00,0x3b430000,0x4afb4b30,0x47d24705,
0x4be24bf3,0x416c3f40,0x4a7e4abf,0x48ad484d,0x4bae4bcb,0x447b4334,0x49eb4a37,0x49624909,0x4b604b8a,0x46314558,0x4946499b,0x4a0449b5,
0x4bfc4c00,0x3c060000,0x4ac14b02,0x484a47b7,0x4bdc4bf0,0x42014004,0x4a294a78,0x491b48b5,0x4b9c4bc0,0x44f343f7,0x497949d4,0x49d6497b,
0x4b3d4b70,0x46d245e5,0x48b24918,0x4a7a4a2b,0x4bfb4c00,0x3c6a0000,0x4a814ad0,0x48a84832,0x4bd44bed,0x42944067,0x49cd4a2b,0x49824918,
0x4b874bb2,0x456a445d,0x48fd4969,0x4a4149e5,0x4b164b53,0x476f4670,0x4815488c,0x4ae14a95,0x4bfa4c00,0x3cce0000,0x4a3d4a99,0x49024887,
0x4bcc4be9,0x432840cb,0x496b49d8,0x49e34976,0x4b714ba4,0x45df44bd,0x487a48f6,0x4aa24a47,0x4aeb4b33,0x480546f9,0x46dd47ee,0x4b3a4af3,
0x4bf94c00,0x3d330000,0x49f44a5e,0x495848d8,0x4bc34be5,0x43ba412e,0x49024980,0x4a3d49d0,0x4b594b95,0x4654451d,0x47dd487c,0x4af74aa0,
0x4abd4b11,0x48504780,0x458146b5,0x4b834b43,0x4bf84c00,0x3d970000,0x49a64a1f,0x49aa4927,0x4bba4be1,0x44264191,0x48944922,0x4a904a23,
0x4b3f4b84,0x46c6457c,0x46bb47f9,0x4b424af0,0x4a8c4aed,0x48994802,0x441a4570,0x4bbc4b86,0x4bf74c00,0x3dfb0000,0x495449dc,0x49f84972,
0x4bb04bdc,0x446f41f4,0x482048bf,0x4adb4a71,0x4b244b72,0x473745da,0x458d46ee,0x4b814b36,0x4a584ac6,0x48e04842,0x41534420,0x4be34bbb,
0x4bf64c00,0x3e5f0000,0x48fd4996,0x4a4149ba,0x4ba54bd7,0x44b74257,0x474e4858,0x4b1e4ab8,0x4b074b5f,0x47a64637,0x445745da,0x4bb34b72,
0x4a214a9c,0x49244881,0x3cce4191,0x4bfa4be1,0x4bf54c00,0x3ec30000,0x48a3494d,0x4a8549fe,0x4b9a4bd2,0x44ff42b9,0x465447d8,0x4b594af9,
0x4ae84b4b,0x480a4693,0x423244bd,0x4bd94ba4,0x49e74a71,0x496648bf,0xb4523db0,0x4c004bf8,0x4bf34c00,0x3f270000,0x48454900,0x4ac44a3f,
0x4b8e4bcd,0x4546431b,0x455246f9,0x4b8b4b33,0x4ac74b36,0x484046ee,0x3f594334,0x4bf24bcb,0x49aa4a43,0x49a648fb,0xbef52a48,0x4bf44c00,
0x4bf24c00,0x3f8b0000,0x47c848b0,0x4afe4a7c,0x4b814bc7,0x458d437d,0x444b4614,0x4bb54b67,0x4aa54b20,0x48744748,0x388440e4,0x4bff4be8,
0x496b4a13,0x49e34935,0xc263bd4c,0x4bd74bf9,0x4bf04c00,0x3fef0000,0x46ff485d,0x4b324ab5,0x4b734bc1,0x45d443df,0x427c4529,0x4bd64b93,
0x4a814b08,0x48a847a1,0xb9b13d1a,0x4bfe4bf9,0x492949e1,0x4a1d496d,0xc49fc160,0x4ba94be3,0x4bef4c00,0x40290000,0x46314807,0x4b604ae9,
0x4b654bbb,0x461a4420,0x405b4438,0x4bed4bb7,0x4a5c4af0,0x48db47f9,0xbfef2e48,0x4bf04c00,0x48e549ad,0x4a5449a4,0xc602c408,0x4b6a4bbe,
0x4bed4c00,0x405b0000,0x455e475e,0x4b894b1a,0x4b574bb4,0x465f4451,0x3c6a4288,0x4bfb4bd5,0x4a354ad6,0x490c4828,0xc27cbc51,0x4bd64bfb,
0x489e4976,0x4a8949d8,0xc759c558,0x4b1b4b8a,0x4beb4c00,0x408d0000,0x448746aa,0x4bac4b46,0x4b474bad,0x46a44481,0x26484099,0x4c004beb,
0x4a0d4abc,0x493c4852,0xc47bc080,0x4bae4bec,0x4855493e,0x4aba4a0b,0xc850c69e,0x4abd4b49,0x4be94c00,0x40be0000,0x435945f1,0x4bc94b6e,
0x4b374ba6,0x46e844b1,0xbc383d4c,0x4bfc4bf9,0x49e34aa0,0x496b487c,0xc5b1c2d2,0x4b7a4bd1,0x480a4905,0x4ae84a3b,0xc8eac7d8,0x4a504af9,
0x4be74c00,0x40f00000,0x419e4534,0x4be04b91,0x4b274b9e,0x472c44e1,0xc042357f,0x4bee4c00,0x49b84a83,0x499948a6,0xc6ddc48d,0x4b3a4bab,
0x477a48c9,0x4b134a69,0xc979c881,0x49d64a9c,0x4be54c00,0x41220000,0x3fbd4475,0x4bf14baf,0x4b164b97,0x476f4511,0xc263b91b,0x4bd74bfe,
0x498b4a65,0x49c548ce,0xc7fec5ab,0x4aee4b7b,0x46dd488c,0x4b3a4a95,0xc9fcc90e,0x494f4a33,0x4be34c00,0x41530000,0x3c384365,0x4bfc4bc9,
0x4b044b8f,0x47b24540,0xc43ebe78,0x4bb74bf6,0x495d4a47,0x49f048f6,0xc889c6c1,0x4a974b41,0x463c484d,0x4b5e4abf,0xca73c992,0x48bc49be,
0x4be14c00,0x41850000,0x317f41db,0x4c004bdd,0x4af14b86,0x47f34570,0xc546c12e,0x4b8e4be5,0x492e4a27,0x4a19491d,0xc90cc7cd,0x4a354afc,
0x4599480d,0x4b7f4ae6,0xcadbca0b,0x4820493e,0x4bdf4c00,0x41b60000,0xb9b1404e,0x4bfe4bed,0x4ade4b7d,0x481a459f,0xc648c31b,0x4b5c4bcd,
0x48fd4a07,0x4a414943,0xc986c867,0x49c94aae,0x44f34796,0x4b9c4b0b,0xcb35ca78,0x46f448b5,0x4bdd4c00,0x41e80000,0xbe5f3d7e,0x4bf64bf8,
0x4acb4b74,0x483a45ce,0xc742c481,0x4b214bad,0x48cc49e5,0x4a674969,0xc9f8c8e2,0x49544a56,0x444b4710,0x4bb54b2e,0xcb7fcad9,0x45994822,
0x4bda4c00,0x42190000,0xc0f038b6,0x4be74bff,0x4ab64b6b,0x485a45fd,0xc81ac570,0x4ade4b86,0x489949c3,0x4a8c498d,0xca60c956,0x48d649f6,
0x43404687,0x4bcb4b4e,0xcbb8cb2e,0x44324710,0x4bd84c00,0x424b0000,0xc2adb248,0x4bd34c00,0x4aa24b62,0x487a462b,0xc88ec659,0x4a934b58,
0x4865499f,0x4ab049b1,0xcabdc9c3,0x4850498d,0x41e845fd,0x4bdd4b6b,0xcbe1cb74,0x418545ce,0x4bd64c00,0x427c0000,0xc432bbd9,0x4bb84bfc,
0x4a8c4b58,0x48994659,0xc8fdc73d,0x4a414b22,0x4830497b,0x4ad149d4,0xcb10ca27,0x4785491d,0x408d4570,0x4beb4b86,0xcbf9cbad,0x3d334481,
0x4bd34c00,0x42ad0000,0xc50bbf0e,0x4b984bf4,0x4a764b4e,0x48b74687,0xc966c80d,0x49e74ae6,0x47f34956,0x4af149f6,0xcb57ca83,0x465f48a6,
0x3e5f44e1,0x4bf64b9e,0xcc00cbd7,0xb17f4257,0x4bd04c00,0x42de0000,0xc5dfc115,0x4b714be6,0x4a604b43,0x48d646b5,0xc9c9c877,0x49864aa3,
0x47854930,0x4b104a17,0xcb92cad6,0x452f4828,0x3b434451,0x4bfd4bb4,0xcbf5cbf3,0xbe913f40,0x4bce4c00,0x430f0000,0xc6afc2a1,0x4b454bd4,
0x4a494b39,0x48f346e3,0xca25c8dd,0x491f4a5a,0x47154909,0x4b2c4a37,0xcbc0cb20,0x43eb4748,0x3311437d,0x4c004bc7,0xcbd9cbff,0xc2323711,
0x4bcb4c00,0x43400000,0xc77ac414,0x4b134bbc,0x4a314b2e,0x49114710,0xca7ac93e,0x48b24a0b,0x46a448e2,0x4b474a56,0xcbe2cb5f,0x416c4637,
0xb7764257,0x4bff4bd7,0xcbaccbfd,0xc487bb75,0x4bc84c00,0x43710000,0xc820c4d5,0x4adb4ba0,0x4a194b22,0x492e473d,0xcac7c99b,0x484049b5,
0x463148ba,0x4b604a74,0xcbf8cb95,0x3dc9451d,0xbc9c412e,0x4bfb4be5,0xcb6fcbeb,0xc5ebc099,0x4bc54c00,0x43a20000,0xc87fc593,0x4a9e4b80,
0x4a004b17,0x494a476a,0xcb0dc9f2,0x4790495b,0x45bc4891,0x4b784a92,0xcc00cbc0,0x317f43f7,0xbf594004,0x4bf24bf0,0xcb21cbca,0xc742c34c,
0x4bc24c00,0x43d30000,0xc8dbc64e,0x4a5c4b5a,0x49e74b0b,0x49664796,0xcb4aca43,0x469948fb,0x45464867,0x4b8e4aae,0xcbfbcbe0,0xbc6a41aa,
0xc1093db0,0x4be64bf8,0xcac4cb9b,0xc845c4f9,0x4bbf4c00,0x44020000,0xc933c705,0x4a154b30,0x49cd4aff,0x498247c2,0xcb7fca8e,0x45994896,
0x44cf483d,0x4ba14ac9,0xcbe9cbf5,0xc0be3eaa,0xc2633aac,0x4bd74bfd,0xca58cb5d,0xc8e0c642,0x4bbc4c00,0x441a0000,0xc986c7b7,0x49c94b02,
0x49b34af3,0x499d47ee,0xcbabcad3,0x4493482d,0x44574812,0x4bb34ae3,0xcbcbcbff,0xc34037da,0xc3ba33db,0x4bc34c00,0xc9dfcb11,0xc970c780,
0x4bb84c00,0x44320000,0xc9d6c832,0x49794ad0,0x49994ae6,0x49b8480d,0xcbcecb11,0x430f4780,0x43ba47cd,0x4bc34afc,0xcb9fcbfe,0xc4dbb97f,
0xc487b57f,0x4bac4c00,0xc958cab8,0xc9f4c858,0x4bb54c00,0x444b0000,0xca21c887,0x49244a99,0x497d4ad9,0x49d24822,0xcbe7cb49,0x40f0469e,
0x42c64775,0x4bd24b14,0xcb68cbf2,0xc60ebf72,0xc52fbb75,0x4b924bfd,0xc8c7ca52,0xca6bc8e7,0x4bb24c00,0x44630000,0xca67c8d8,0x48cc4a5e,
0x49624acc,0x49eb4838,0xcbf8cb79,0x3d9745b6,0x41cf471b,0x4bde4b2b,0xcb24cbdb,0xc737c20d,0xc5d4be14,0x4b734bf7,0xc82ac9e1,0xcad5c96d,
0x4bae4c00,0x447b0000,0xcaa9c927,0x486f4a1f,0x49464abf,0x4a04484d,0xcc00cba2,0x351b44c9,0x40d746c1,0x4be84b41,0xcad5cbb9,0xc82ac42c,
0xc676c036,0x4b524bee,0xc70ac964,0xcb2fc9e9,0x4bab4c00,0x44930000,0xcae5c972,0x480f49dc,0x49294ab1,0x4a1d4862,0xcbfecbc4,0xba1643ae,
0x3fbd4665,0x4bf14b55,0xca7acb8c,0xc8b2c54c,0xc715c160,0x4b2c4be3,0xc5b1c8dd,0xcb7aca5a,0x4ba74c00,0x44ab0000,0xcb1bc9ba,0x47594996,
0x490c4aa3,0x4a354877,0xcbf2cbdf,0xbf5941c3,0x3dc94608,0x4bf84b69,0xca15cb55,0xc933c665,0xc7b2c288,0x4b044bd5,0xc44bc84d,0xcbb5cabf,
0x4ba34c00,0x44c30000,0xcb4cc9fe,0x468d494d,0x48ee4a95,0x4a4d488c,0xcbdecbf1,0xc1cf3fa4,0x3ba745ab,0x4bfc4b7b,0xc9a6cb14,0xc9aac775,
0xc825c3ae,0x4ad84bc4,0xc1b6c76a,0xcbdfcb17,0x4b9f4c00,0x44db0000,0xcb78ca3f,0x45bc4900,0x48d14a87,0x4a6448a0,0xcbc0cbfd,0xc3eb3b75,
0x3776454c,0x4bff4b8c,0xc92ecac9,0xca19c83d,0xc86fc469,0x4aa94bb1,0xbd97c62b,0xcbf8cb62,0x4b9c4c00,0x44f30000,0xcb9eca7c,0x44e748b0,
0x48b24a78,0x4a7a48b5,0xcb9acc00,0xc4ffaa48,0xa64844ed,0x4c004b9d,0xc8adca74,0xca7ec8ba,0xc8b7c4f9,0x4a764b9b,0x2cb6c4e1,0xcc00cb9e,
0x4b984c00,0x450b0000,0xcbbdcab5,0x440e485d,0x48944a69,0x4a9048c9,0xcb6acbfc,0xc602bc1f,0xb81f448d,0x4bff4bab,0xc825ca17,0xcad8c930,
0xc8fdc587,0x4a414b82,0x3e2dc31b,0xcbf6cbcd,0x4b944c00,0x45230000,0xcbd7cae9,0x42634807,0x48744a5a,0x4aa548dd,0xcb32cbf0,0xc6ffc004,
0xbc06442c,0x4bfc4bb9,0xc72cc9b1,0xcb27c99f,0xc941c614,0x4a094b67,0x4201c067,0xcbdccbed,0x4b904c00,0x453a0000,0xcbeacb1a,0x40a6475e,
0x48554a4b,0x4aba48f1,0xcaf1cbdc,0xc7f3c1f4,0xbdfb4396,0x4bf74bc6,0xc602c943,0xcb6aca07,0xc982c69e,0x49cd4b49,0x446fbaac,0xcbb0cbfd,
0x4b8b4c00,0x45520000,0xcbf8cb46,0x3dc946aa,0x48354a3b,0x4ace4905,0xcaa9cbc1,0xc86fc3df,0xbfef42d2,0x4bf04bd1,0xc4cfc8ce,0xcba1ca65,
0xc9c0c726,0x49904b28,0x45d43852,0xcb73cbff,0x4b874c00,0x456a0000,0xcbffcb6e,0x388445f1,0x48154a2b,0x4ae14918,0xca58cb9e,0xc8e0c4e1,
0xc0f0420d,0x4be74bdb,0xc328c852,0xcbcccabc,0xc9fcc7ac,0x494f4b05,0x472c3fa4,0xcb27cbf1,0x4b834c00,0x45810000,0xcc00cb91,0xb51b4534,
0x47e84a1b,0x4af4492b,0xca00cb74,0xc94ac5ce,0xc1e84147,0x4bdd4be4,0xc0a6c7a1,0xcbeacb08,0xca35c817,0x490c4ae0,0x483a4288,0xcacbcbd5,
0x4b7f4c00,0x45990000,0xcbfacbaf,0xbcce4475,0x47a64a0b,0x4b07493e,0xc9a1cb43,0xc9afc6b5,0xc2de4080,0x4bd04bec,0xbc38c693,0xcbfccb4b,
0xca6bc858,0x48c74ab8,0x48d64499,0xca60cbaa,0x4b7a4c00,0x45b10000,0xcbefcbc9,0xc0294365,0x476449fa,0x4b184951,0xc93ccb0b,0xca0dc796,
0xc3d33f72,0x4bc24bf2,0x3311c57c,0xcc00cb84,0xca9ec896,0x487f4a8e,0x496645e5,0xc9e7cb70,0x4b764c00,0x45c80000,0xcbddcbdd,0xc1e841db,
0x472149e9,0x4b2a4964,0xc8d1cacc,0xca64c838,0xc4633de2,0x4bb24bf7,0x3dfbc45d,0xcbf7cbb2,0xcacec8d3,0x48354a62,0x49eb4726,0xc962cb28,
0x4b714c00,0x45df0000,0xcbc5cbed,0xc3a2404e,0x46dd49d8,0x4b3a4976,0xc85fca87,0xcab3c8a0,0xc4db3c51,0x4b9f4bfb,0x4185c26f,0xcbe1cbd6,
0xcafbc90e,0x47d24a33,0x4a64482d,0xc8d1cad3,0x4b6c4c00,0x45f70000,0xcba7cbf8,0xc4ab3d7e,0x469949c7,0x4b4a4989,0xc7d2ca3b,0xcafbc905,
0xc552397f,0x4b8b4bfe,0x4402c01d,0xcbbfcbef,0xcb24c948,0x47374a02,0x4ace48bf,0xc835ca71,0x4b684c00,0x460e0000,0xcb83cbff,0xc58138b6,
0x465449b5,0x4b59499b,0xc6ddc9e9,0xcb3ac964,0xc5c834b6,0x4b764c00,0x453abb11,0xcb90cbfd,0xcb4ac980,0x469949d0,0x4b2a4948,0xc721ca02,
0x2c002c00,0x2c002c00,0x2c002c00,0x2c002c00,0x2b642c00,0x261f29a8,0xa61f0000,0xab64a9a8,0x29a82c00,0xa9a80000,0xa9a8ac00,0x29a80000,
0x261f2c00,0xab64a9a8,0x2b640000,0xa61f29a8,0x2c00,0xac00,0x2c00,0xac00,0xa61f2c00,0x2b64a9a8,0xab640000,0x261f29a8,
0xa9a82c00,0x29a80000,0x29a8ac00,0xa9a80000,0xab642c00,0xa61f29a8,0x261f0000,0x2b64a9a8,0,0,0,0,
0x261f0000,0x2b6429a8,0x2b642c00,0x261f29a8,0x29a80000,0x29a82c00,0xa9a80000,0xa9a8ac00,0x2b640000,0xa61f29a8,0xa61fac00,0x2b6429a8,
0x2c000000,0xac000000,0x2c000000,0xac000000,0x2b640000,0xa61fa9a8,0xa61f2c00,0x2b64a9a8,0x29a80000,0x29a8ac00,0xa9a80000,0xa9a82c00,
0x261f0000,0x2b64a9a8,0x2b64ac00,0x261fa9a8,0xac002c00,0xac002c00,0xac002c00,0xac002c00,0xab642c00,0xa61f29a8,0x261f0000,0x2b64a9a8,
0xa9a82c00,0x29a80000,0x29a8ac00,0xa9a80000,0xa61f2c00,0x2b64a9a8,0xab640000,0x261f29a8,0x2c00,0xac00,0x2c00,0xac00,
0x261f2c00,0xab64a9a8,0x2b640000,0xa61f29a8,0x29a82c00,0xa9a80000,0xa9a8ac00,0x29a80000,0x2b642c00,0x261f29a8,0xa61f0000,0xab64a9a8,
0,0,0,0,0xa61f0000,0xab6429a8,0xab642c00,0xa61f29a8,0xa9a80000,0xa9a82c00,0x29a80000,0x29a8ac00,
0xab640000,0x261f29a8,0x261fac00,0xab6429a8,0xac000000,0x2c000000,0xac000000,0x2c000000,0xab640000,0x261fa9a8,0x261f2c00,0xab64a9a8,
0xa9a80000,0xa9a8ac00,0x29a80000,0x29a82c00,0xa61f0000,0xab64a9a8,0xab64ac00,0xa61fa9a8,0,0,0,0,
0xa61f0000,0xab64a9a8,0xab64ac00,0xa61fa9a8,0xa9a80000,0xa9a8ac00,0x29a80000,0x29a82c00,0xab640000,0x261fa9a8,0x261f2c00,0xab64a9a8,
0xac000000,0x2c000000,0xac000000,0x2c000000,0xab640000,0x261f29a8,0x261fac00,0xab6429a8,0xa9a80000,0xa9a82c00,0x29a80000,0x29a8ac00,
0xa61f0000,0xab6429a8,0xab642c00,0xa61f29a8,0x2c002c00,0x2c002c00,0x2c002c00,0x2c002c00,0x2b642c00,0x261f29a8,0xa61f0000,0xab64a9a8,
0x29a82c00,0xa9a80000,0xa9a8ac00,0x29a80000,0x261f2c00,0xab64a9a8,0x2b640000,0xa61f29a8,0x2c00,0xac00,0x2c00,0xac00,
0xa61f2c00,0x2b64a9a8,0xab640000,0x261f29a8,0xa9a82c00,0x29a80000,0x29a8ac00,0xa9a80000,0xab642c00,0xa61f29a8,0x261f0000,0x2b64a9a8,
0,0,0,0,0x261f0000,0x2b64a9a8,0x2b64ac00,0x261fa9a8,0x29a80000,0x29a8ac00,0xa9a80000,0xa9a82c00,
0x2b640000,0xa61fa9a8,0xa61f2c00,0x2b64a9a8,0x2c000000,0xac000000,0x2c000000,0xac000000,0x2b640000,0xa61f29a8,0xa61fac00,0x2b6429a8,
0x29a80000,0x29a82c00,0xa9a80000,0xa9a8ac00,0x261f0000,0x2b6429a8,0x2b642c00,0x261f29a8,0xac002c00,0xac002c00,0xac002c00,0xac002c00,
0xab642c00,0xa61f29a8,0x261f0000,0x2b64a9a8,0xa9a82c00,0x29a80000,0x29a8ac00,0xa9a80000,0xa61f2c00,0x2b64a9a8,0xab640000,0x261f29a8,
0x2c00,0xac00,0x2c00,0xac00,0x261f2c00,0xab64a9a8,0x2b640000,0xa61f29a8,0x29a82c00,0xa9a80000,0xa9a8ac00,0x29a80000,
0x2b642c00,0x261f29a8,0xa61f0000,0xab64a9a8,0x2c002c00,0x2c002c00,0x2c002c00,0x2c002c00,0xab64ac00,0xa61fa9a8,0x261f0000,0x2b6429a8,
0x29a82c00,0xa9a80000,0xa9a8ac00,0x29a80000,0xa61fac00,0x2b6429a8,0xab640000,0x261fa9a8,0x2c00,0xac00,0x2c00,0xac00,
0x261fac00,0xab6429a8,0x2b640000,0xa61fa9a8,0xa9a82c00,0x29a80000,0x29a8ac00,0xa9a80000,0x2b64ac00,0x261fa9a8,0xa61f0000,0xab6429a8,
0,0,0,0,0xa61f0000,0xab64a9a8,0xab64ac00,0xa61fa9a8,0x29a80000,0x29a82c00,0xa9a80000,0xa9a8ac00,
0xab640000,0x261fa9a8,0x261f2c00,0xab64a9a8,0x2c000000,0xac000000,0x2c000000,0xac000000,0xab640000,0x261f29a8,0x261fac00,0xab6429a8,
0x29a80000,0x29a8ac00,0xa9a80000,0xa9a82c00,0xa61f0000,0xab6429a8,0xab642c00,0xa61f29a8,0xac002c00,0xac002c00,0xac002c00,0xac002c00,
0x2b64ac00,0x261fa9a8,0xa61f0000,0xab6429a8,0xa9a82c00,0x29a80000,0x29a8ac00,0xa9a80000,0x261fac00,0xab6429a8,0x2b640000,0xa61fa9a8,
0x2c00,0xac00,0x2c00,0xac00,0xa61fac00,0x2b6429a8,0xab640000,0x261fa9a8,0x29a82c00,0xa9a80000,0xa9a8ac00,0x29a80000,
0xab64ac00,0xa61fa9a8,0x261f0000,0x2b6429a8,0,0,0,0,0x261f0000,0x2b64a9a8,0x2b64ac00,0x261fa9a8,
0xa9a80000,0xa9a82c00,0x29a80000,0x29a8ac00,0x2b640000,0xa61fa9a8,0xa61f2c00,0x2b64a9a8,0xac000000,0x2c000000,0xac000000,0x2c000000,
0x2b640000,0xa61f29a8,0xa61fac00,0x2b6429a8,0xa9a80000,0xa9a8ac00,0x29a80000,0x29a82c00,0x261f0000,0x2b6429a8,0x2b642c00,0x261f29a8,
0,0,0,0,0x261f0000,0x2b6429a8,0x2b642c00,0x261f29a8,0xa9a80000,0xa9a8ac00,0x29a80000,0x29a82c00,
0x2b640000,0xa61f29a8,0xa61fac00,0x2b6429a8,0xac000000,0x2c000000,0xac000000,0x2c000000,0x2b640000,0xa61fa9a8,0xa61f2c00,0x2b64a9a8,
0xa9a80000,0xa9a82c00,0x29a80000,0x29a8ac00,0x261f0000,0x2b64a9a8,0x2b64ac00,0x261fa9a8,0x2c002c00,0x2c002c00,0x2c002c00,0x2c002c00,
0xab64ac00,0xa61fa9a8,0x261f0000,0x2b6429a8,0x29a82c00,0xa9a80000,0xa9a8ac00,0x29a80000,0xa61fac00,0x2b6429a8,0xab640000,0x261fa9a8,
0x2c00,0xac00,0x2c00,0xac00,0x261fac00,0xab6429a8,0x2b640000,0xa61fa9a8,0xa9a82c00,0x29a80000,0x29a8ac00,0xa9a80000,
0x2b64ac00,0x261fa9a8,0xa61f0000,0xab6429a8,0,0,0,0,0xa61f0000,0xab6429a8,0xab642c00,0xa61f29a8,
0x29a80000,0x29a8ac00,0xa9a80000,0xa9a82c00,0xab640000,0x261f29a8,0x261fac00,0xab6429a8,0x2c000000,0xac000000,0x2c000000,0xac000000,
0xab640000,0x261fa9a8,0x261f2c00,0xab64a9a8,0x29a80000,0x29a82c00,0xa9a80000,0xa9a8ac00,0xa61f0000,0xab64a9a8,0xab64ac00,0xa61fa9a8,
0xac002c00,0xac002c00,0xac002c00,0xac002c00,0x2b64ac00,0x261fa9a8,0xa61f0000,0xab6429a8,0xa9a82c00,0x29a80000,0x29a8ac00,0xa9a80000,
0x261fac00,0xab6429a8,0x2b640000,0xa61fa9a8,0x2c00,0xac00,0x2c00,0xac00,0xa61fac00,0x2b6429a8,0xab640000,0x261fa9a8,
0x29a82c00,0xa9a80000,0xa9a8ac00,0x29a80000,0xab64ac00,0xa61fa9a8,0x261f0000,0x2b6429a8,0x2bd92c00,0x2aa72b64,0x287229a8,0x223e261f,
0x2aa72c00,0xa23e261f,0xabd9a9a8,0xa872ab64,0x28722c00,0xabd9a61f,0x223ea9a8,0x2aa72b64,0x223e2c00,0xa872ab64,0x2aa729a8,0xabd9a61f,
0xa23e2c00,0x2872ab64,0xaaa729a8,0x2bd9a61f,0xa8722c00,0x2bd9a61f,0xa23ea9a8,0xaaa72b64,0xaaa72c00,0x223e261f,0x2bd9a9a8,0x2872ab64,
0xabd92c00,0xaaa72b64,0xa87229a8,0xa23e261f,0x223e0000,0x2872261f,0x2aa729a8,0x2bd92b64,0x28720000,0x2bd92b64,0x223e29a8,0xaaa7a61f,
0x2aa70000,0x223e2b64,0xabd9a9a8,0x2872a61f,0x2bd90000,0xaaa7261f,0x2872a9a8,0xa23e2b64,0x2bd90000,0xaaa7a61f,0x287229a8,0xa23eab64,
0x2aa70000,0x223eab64,0xabd929a8,0x2872261f,0x28720000,0x2bd9ab64,0x223ea9a8,0xaaa7261f,0x223e0000,0x2872a61f,0x2aa7a9a8,0x2bd9ab64,
0xabd92c00,0xaaa72b64,0xa87229a8,0xa23e261f,0xaaa72c00,0x223e261f,0x2bd9a9a8,0x2872ab64,0xa8722c00,0x2bd9a61f,0xa23ea9a8,0xaaa72b64,
0xa23e2c00,0x2872ab64,0xaaa729a8,0x2bd9a61f,0x223e2c00,0xa872ab64,0x2aa729a8,0xabd9a61f,0x28722c00,0xabd9a61f,0x223ea9a8,0x2aa72b64,
0x2aa72c00,0xa23e261f,0xabd9a9a8,0xa872ab64,0x2bd92c00,0x2aa72b64,0x287229a8,0x223e261f,0xa23e0000,0xa872261f,0xaaa729a8,0xabd92b64,
0xa8720000,0xabd92b64,0xa23e29a8,0x2aa7a61f,0xaaa70000,0xa23e2b64,0x2bd9a9a8,0xa872a61f,0xabd90000,0x2aa7261f,0xa872a9a8,0x223e2b64,
0xabd90000,0x2aa7a61f,0xa87229a8,0x223eab64,0xaaa70000,0xa23eab64,0x2bd929a8,0xa872261f,0xa8720000,0xabd9ab64,0xa23ea9a8,0x2aa7261f,
0xa23e0000,0xa872a61f,0xaaa7a9a8,0xabd9ab64,0xa23e0000,0xa872a61f,0xaaa7a9a8,0xabd9ab64,0xa8720000,0xabd9ab64,0xa23ea9a8,0x2aa7261f,
0xaaa70000,0xa23eab64,0x2bd929a8,0xa872261f,0xabd90000,0x2aa7a61f,0xa87229a8,0x223eab64,0xabd90000,0x2aa7261f,0xa872a9a8,0x223e2b64,
0xaaa70000,0xa23e2b64,0x2bd9a9a8,0xa872a61f,0xa8720000,0xabd92b64,0xa23e29a8,0x2aa7a61f,0xa23e0000,0xa872261f,0xaaa729a8,0xabd92b64,
0x2bd92c00,0x2aa72b64,0x287229a8,0x223e261f,0x2aa72c00,0xa23e261f,0xabd9a9a8,0xa872ab64,0x28722c00,0xabd9a61f,0x223ea9a8,0x2aa72b64,
0x223e2c00,0xa872ab64,0x2aa729a8,0xabd9a61f,0xa23e2c00,0x2872ab64,0xaaa729a8,0x2bd9a61f,0xa8722c00,0x2bd9a61f,0xa23ea9a8,0xaaa72b64,
0xaaa72c00,0x223e261f,0x2bd9a9a8,0x2872ab64,0xabd92c00,0xaaa72b64,0xa87229a8,0xa23e261f,0x223e0000,0x2872a61f,0x2aa7a9a8,0x2bd9ab64,
0x28720000,0x2bd9ab64,0x223ea9a8,0xaaa7261f,0x2aa70000,0x223eab64,0xabd929a8,0x2872261f,0x2bd90000,0xaaa7a61f,0x287229a8,0xa23eab64,
0x2bd90000,0xaaa7261f,0x2872a9a8,0xa23e2b64,0x2aa70000,0x223e2b64,0xabd9a9a8,0x2872a61f,0x28720000,0x2bd92b64,0x223e29a8,0xaaa7a61f,
0x223e0000,0x2872261f,0x2aa729a8,0x2bd92b64,0xabd92c00,0xaaa72b64,0xa87229a8,0xa23e261f,0xaaa72c00,0x223e261f,0x2bd9a9a8,0x2872ab64,
0xa8722c00,0x2bd9a61f,0xa23ea9a8,0xaaa72b64,0xa23e2c00,0x2872ab64,0xaaa729a8,0x2bd9a61f,0x223e2c00,0xa872ab64,0x2aa729a8,0xabd9a61f,
0x28722c00,0xabd9a61f,0x223ea9a8,0x2aa72b64,0x2aa72c00,0xa23e261f,0xabd9a9a8,0xa872ab64,0x2bd92c00,0x2aa72b64,0x287229a8,0x223e261f,
0xa23e0000,0xa872a61f,0xaaa7a9a8,0xabd9ab64,0x28720000,0x2bd92b64,0x223e29a8,0xaaa7a61f,0xaaa70000,0xa23eab64,0x2bd929a8,0xa872261f,
0x2bd90000,0xaaa7261f,0x2872a9a8,0xa23e2b64,0xabd90000,0x2aa7261f,0xa872a9a8,0x223e2b64,0x2aa70000,0x223eab64,0xabd929a8,0x2872261f,
0xa8720000,0xabd92b64,0xa23e29a8,0x2aa7a61f,0x223e0000,0x2872a61f,0x2aa7a9a8,0x2bd9ab64,0x2bd92c00,0x2aa72b64,0x287229a8,0x223e261f,
0xaaa7ac00,0x223ea61f,0x2bd929a8,0x28722b64,0x28722c00,0xabd9a61f,0x223ea9a8,0x2aa72b64,0xa23eac00,0x28722b64,0xaaa7a9a8,0x2bd9261f,
0xa23e2c00,0x2872ab64,0xaaa729a8,0x2bd9a61f,0x2872ac00,0xabd9261f,0x223e29a8,0x2aa7ab64,0xaaa72c00,0x223e261f,0x2bd9a9a8,0x2872ab64,
0x2bd9ac00,0x2aa7ab64,0x2872a9a8,0x223ea61f,0x223e0000,0x2872a61f,0x2aa7a9a8,0x2bd9ab64,0xa8720000,0xabd92b64,0xa23e29a8,0x2aa7a61f,
0x2aa70000,0x223eab64,0xabd929a8,0x2872261f,0xabd90000,0x2aa7261f,0xa872a9a8,0x223e2b64,0x2bd90000,0xaaa7261f,0x2872a9a8,0xa23e2b64,
0xaaa70000,0xa23eab64,0x2bd929a8,0xa872261f,0x28720000,0x2bd92b64,0x223e29a8,0xaaa7a61f,0xa23e0000,0xa872a61f,0xaaa7a9a8,0xabd9ab64,
0xabd92c00,0xaaa72b64,0xa87229a8,0xa23e261f,0x2aa7ac00,0xa23ea61f,0xabd929a8,0xa8722b64,0xa8722c00,0x2bd9a61f,0xa23ea9a8,0xaaa72b64,
0x223eac00,0xa8722b64,0x2aa7a9a8,0xabd9261f,0x223e2c00,0xa872ab64,0x2aa729a8,0xabd9a61f,0xa872ac00,0x2bd9261f,0xa23e29a8,0xaaa7ab64,
0x2aa72c00,0xa23e261f,0xabd9a9a8,0xa872ab64,0xabd9ac00,0xaaa7ab64,0xa872a9a8,0xa23ea61f,0xabd9ac00,0xaaa7ab64,0xa872a9a8,0xa23ea61f,
0x2aa72c00,0xa23e261f,0xabd9a9a8,0xa872ab64,0xa872ac00,0x2bd9261f,0xa23e29a8,0xaaa7ab64,0x223e2c00,0xa872ab64,0x2aa729a8,0xabd9a61f,
0x223eac00,0xa8722b64,0x2aa7a9a8,0xabd9261f,0xa8722c00,0x2bd9a61f,0xa23ea9a8,0xaaa72b64,0x2aa7ac00,0xa23ea61f,0xabd929a8,0xa8722b64,
0xabd92c00,0xaaa72b64,0xa87229a8,0xa23e261f,0xa23e0000,0xa872a61f,0xaaa7a9a8,0xabd9ab64,0x28720000,0x2bd92b64,0x223e29a8,0xaaa7a61f,
0xaaa70000,0xa23eab64,0x2bd929a8,0xa872261f,0x2bd90000,0xaaa7261f,0x2872a9a8,0xa23e2b64,0xabd90000,0x2aa7261f,0xa872a9a8,0x223e2b64,
0x2aa70000,0x223eab64,0xabd929a8,0x2872261f,0xa8720000,0xabd92b64,0xa23e29a8,0x2aa7a61f,0x223e0000,0x2872a61f,0x2aa7a9a8,0x2bd9ab64,
0x2bd9ac00,0x2aa7ab64,0x2872a9a8,0x223ea61f,0xaaa72c00,0x223e261f,0x2bd9a9a8,0x2872ab64,0x2872ac00,0xabd9261f,0x223e29a8,0x2aa7ab64,
0xa23e2c00,0x2872ab64,0xaaa729a8,0x2bd9a61f,0xa23eac00,0x28722b64,0xaaa7a9a8,0x2bd9261f,0x28722c00,0xabd9a61f,0x223ea9a8,0x2aa72b64,
0xaaa7ac00,0x223ea61f,0x2bd929a8,0x28722b64,0x2bd92c00,0x2aa72b64,0x287229a8,0x223e261f,0x223e0000,0x2872a61f,0x2aa7a9a8,0x2bd9ab64,
0xa8720000,0xabd92b64,0xa23e29a8,0x2aa7a61f,0x2aa70000,0x223eab64,0xabd929a8,0x2872261f,0xabd90000,0x2aa7261f,0xa872a9a8,0x223e2b64,
0x2bd90000,0xaaa7261f,0x2872a9a8,0xa23e2b64,0xaaa70000,0xa23eab64,0x2bd929a8,0xa872261f,0x28720000,0x2bd92b64,0x223e29a8,0xaaa7a61f,
0xa23e0000,0xa872a61f,0xaaa7a9a8,0xabd9ab64,0x27fe2800,0x96480000,0x273b2764,0xa2d7a21f,0x27ea27f6,0x9cb29a46,0x26dd270e,0xa41da38b,
0x27c327d9,0x9fc69e3e,0x266d26a7,0xa4c4a472,0x278827a8,0xa164a0a5,0x25ed262f,0xa55fa513,0x27c32800,0x9fc60000,0xa4c4a21f,0xa66da764,
0x25ed270e,0xa55fa38b,0xa73ba62f,0xa2d7a513,0x21642472,0xa788a6a7,0xa7fea7d9,0x16489e3e,0x9cb21a46,0xa7eaa7f6,0xa6dda7a8,0x241d20a5,
0x273b2800,0xa2d70000,0xa55fa764,0x25ed221f,0x1fc62513,0xa7c3a62f,0x1cb2a0a5,0x27ea27a8,0xa4c49e3e,0xa66da7d9,0x26dd2472,0x241d26a7,
0xa7fea70e,0x9648a38b,0x278827f6,0xa1641a46,0x266d2800,0xa4c40000,0x26dd221f,0x241d2764,0xa16420a5,0xa788a7a8,0x25ed27f6,0xa55f9a46,
0xa7fea6a7,0x1648a472,0xa2d71e3e,0xa73ba7d9,0x9fc6a62f,0x27c32513,0xa7eaa70e,0x1cb2a38b,0x255f2800,0xa5ed0000,0x21642764,0xa788a21f,
0xa66d9a46,0xa4c4a7f6,0xa7c3a38b,0x9fc6a70e,0xa41da7d9,0x26dd1e3e,0x9cb2a6a7,0x27ea2472,0x273b20a5,0x22d727a8,0x27fe2513,0x1648262f,
0x241d2800,0xa6dd0000,0xa7eaa21f,0x9cb2a764,0xa7fea38b,0x9648a70e,0x2164a513,0x2788262f,0x22d7a472,0x273b26a7,0x255f27d9,0xa5ed1e3e,
0x24c427f6,0xa66d1a46,0xa7c3a0a5,0x9fc6a7a8,0x21642800,0xa7880000,0x1648a764,0x27fe221f,0xa6dda62f,0x241da513,0x24c427a8,0xa66d20a5,
0x27ea1e3e,0x1cb227d9,0xa7c3a472,0x1fc6a6a7,0xa55f238b,0xa5eda70e,0x273b9a46,0x22d727f6,0x1cb22800,0xa7ea0000,0x27c3221f,0x9fc62764,
0xa2d7a7a8,0x273ba0a5,0xa7fe9a46,0x9648a7f6,0x255f26a7,0xa5ed2472,0x27889e3e,0x216427d9,0xa6dda513,0x241da62f,0xa66d238b,0xa4c4a70e,
0x96482800,0xa7fe0000,0xa2d72764,0xa73ba21f,0x1cb2a7f6,0x27ea1a46,0x241da70e,0x26dd238b,0x9fc627d9,0xa7c39e3e,0xa4c426a7,0xa66da472,
0x2164a7a8,0x278820a5,0x255fa62f,0x25ed2513,0x9fc62800,0xa7c30000,0xa66da21f,0x24c4a764,0x255fa70e,0x25ed238b,0x22d7262f,0xa73b2513,
0xa7882472,0xa164a6a7,0x1648a7d9,0x27fe9e3e,0x27ea9a46,0x9cb227f6,0xa41d27a8,0xa6dda0a5,0xa2d72800,0xa73b0000,0x25eda764,0x255f221f,
0x27c3a513,0x1fc6262f,0xa7ea20a5,0x1cb2a7a8,0xa66d9e3e,0x24c4a7d9,0x241d2472,0xa6dd26a7,0x1648270e,0xa7fe238b,0x2164a7f6,0x27889a46,
0xa4c42800,0xa66d0000,0x241d221f,0xa6dd2764,0x2788a0a5,0xa16427a8,0x255fa7f6,0x25ed1a46,0x1648a6a7,0x27fea472,0xa73b1e3e,0x22d7a7d9,
0xa7c3262f,0x9fc6a513,0x9cb2270e,0xa7ea238b,0xa5ed2800,0xa55f0000,0xa7882764,0xa164a21f,0x24c41a46,0xa66d27f6,0x1fc6238b,0xa7c3270e,
0x26dda7d9,0x241d1e3e,0x27eaa6a7,0x1cb22472,0xa2d7a0a5,0x273ba7a8,0x9648a513,0x27fea62f,0xa6dd2800,0xa41d0000,0x9cb2a21f,0x27eaa764,
0x1648238b,0xa7fe270e,0xa7882513,0x2164a62f,0x273ba472,0xa2d726a7,0xa5ed27d9,0xa55f1e3e,0x266da7f6,0x24c49a46,0x1fc620a5,0xa7c327a8,
0xa7882800,0xa1640000,0x27fea764,0x9648221f,0xa41d262f,0xa6dd2513,0x266da7a8,0x24c4a0a5,0x1cb21e3e,0xa7ea27d9,0x1fc6a472,0x27c3a6a7,
0x25eda38b,0xa55f270e,0xa2d71a46,0x273ba7f6,0xa7ea2800,0x9cb20000,0x9fc6221f,0xa7c32764,0xa73b27a8,0xa2d720a5,0x16481a46,0xa7fe27f6,
0xa5ed26a7,0xa55f2472,0x21649e3e,0xa78827d9,0xa41d2513,0xa6dd262f,0x24c4a38b,0xa66d270e,0xa7fe2800,0x16480000,0xa73b2764,0x22d7a21f,
0xa7ea27f6,0x1cb29a46,0xa6dd270e,0x241da38b,0xa7c327d9,0x1fc69e3e,0xa66d26a7,0x24c4a472,0xa78827a8,0x2164a0a5,0xa5ed262f,0x255fa513,
0xa7c32800,0x1fc60000,0x24c4a21f,0x266da764,0xa5ed270e,0x255fa38b,0x273ba62f,0x22d7a513,0xa1642472,0x2788a6a7,0x27fea7d9,0x96489e3e,
0x1cb21a46,0x27eaa7f6,0x26dda7a8,0xa41d20a5,0xa73b2800,0x22d70000,0x255fa764,0xa5ed221f,0x9fc62513,0x27c3a62f,0x9cb2a0a5,0xa7ea27a8,
0x24c49e3e,0x266da7d9,0xa6dd2472,0xa41d26a7,0x27fea70e,0x1648a38b,0xa78827f6,0x21641a46,0xa66d2800,0x24c40000,0xa6dd221f,0xa41d2764,
0x216420a5,0x2788a7a8,0xa5ed27f6,0x255f9a46,0x27fea6a7,0x9648a472,0x22d71e3e,0x273ba7d9,0x1fc6a62f,0xa7c32513,0x27eaa70e,0x9cb2a38b,
0xa55f2800,0x25ed0000,0xa1642764,0x2788a21f,0x266d9a46,0x24c4a7f6,0x27c3a38b,0x1fc6a70e,0x241da7d9,0xa6dd1e3e,0x1cb2a6a7,0xa7ea2472,
0xa73b20a5,0xa2d727a8,0xa7fe2513,0x9648262f,0xa41d2800,0x26dd0000,0x27eaa21f,0x1cb2a764,0x27fea38b,0x1648a70e,0xa164a513,0xa788262f,
0xa2d7a472,0xa73b26a7,0xa55f27d9,0x25ed1e3e,0xa4c427f6,0x266d1a46,0x27c3a0a5,0x1fc6a7a8,0xa1642800,0x27880000,0x9648a764,0xa7fe221f,
0x26dda62f,0xa41da513,0xa4c427a8,0x266d20a5,0xa7ea1e3e,0x9cb227d9,0x27c3a472,0x9fc6a6a7,0x255f238b,0x25eda70e,0xa73b9a46,0xa2d727f6,
0x9cb22800,0x27ea0000,0xa7c3221f,0x1fc62764,0x22d7a7a8,0xa73ba0a5,0x27fe9a46,0x1648a7f6,0xa55f26a7,0x25ed2472,0xa7889e3e,0xa16427d9,
0x26dda513,0xa41da62f,0x266d238b,0x24c4a70e,0x16482800,0x27fe0000,0x22d72764,0x273ba21f,0x9cb2a7f6,0xa7ea1a46,0xa41da70e,0xa6dd238b,
0x1fc627d9,0x27c39e3e,0x24c426a7,0x266da472,0xa164a7a8,0xa78820a5,0xa55fa62f,0xa5ed2513,0x1fc62800,0x27c30000,0x266da21f,0xa4c4a764,
0xa55fa70e,0xa5ed238b,0xa2d7262f,0x273b2513,0x27882472,0x2164a6a7,0x9648a7d9,0xa7fe9e3e,0xa7ea9a46,0x1cb227f6,0x241d27a8,0x26dda0a5,
0x22d72800,0x273b0000,0xa5eda764,0xa55f221f,0xa7c3a513,0x9fc6262f,0x27ea20a5,0x9cb2a7a8,0x266d9e3e,0xa4c4a7d9,0xa41d2472,0x26dd26a7,
0x9648270e,0x27fe238b,0xa164a7f6,0xa7889a46,0x24c42800,0x266d0000,0xa41d221f,0x26dd2764,0xa788a0a5,0x216427a8,0xa55fa7f6,0xa5ed1a46,
0x9648a6a7,0xa7fea472,0x273b1e3e,0xa2d7a7d9,0x27c3262f,0x1fc6a513,0x1cb2270e,0x27ea238b,0x25ed2800,0x255f0000,0x27882764,0x2164a21f,
0xa4c41a46,0x266d27f6,0x9fc6238b,0x27c3270e,0xa6dda7d9,0xa41d1e3e,0xa7eaa6a7,0x9cb22472,0x22d7a0a5,0xa73ba7a8,0x1648a513,0xa7fea62f,
0x26dd2800,0x241d0000,0x1cb2a21f,0xa7eaa764,0x9648238b,0x27fe270e,0x27882513,0xa164a62f,0xa73ba472,0x22d726a7,0x25ed27d9,0x255f1e3e,
0xa66da7f6,0xa4c49a46,0x9fc620a5,0x27c327a8,0x27882800,0x21640000,0xa7fea764,0x1648221f,0x241d262f,0x26dd2513,0xa66da7a8,0xa4c4a0a5,
0x9cb21e3e,0x27ea27d9,0x9fc6a472,0xa7c3a6a7,0xa5eda38b,0x255f270e,0x22d71a46,0xa73ba7f6,0x27ea2800,0x1cb20000,0x1fc6221f,0x27c32764,
0x273b27a8,0x22d720a5,0x96481a46,0x27fe27f6,0x25ed26a7,0x255f2472,0xa1649e3e,0x278827d9,0x241d2513,0x26dd262f,0xa4c4a38b,0x266d270e,
0x255f25a8,0xa5eda5a8,0x2164221f,0xa788a764,0x24c42513,0xa66da62f,0x1fc620a5,0xa7c3a7a8,0x241d2472,0xa6dda6a7,0x1cb21e3e,0xa7eaa7d9,
0x22d7238b,0xa73ba70e,0x16481a46,0xa7fea7f6,0xa41da5a8,0x26dd25a8,0x27ea2764,0x1cb2221f,0x9648a0a5,0x27fe27a8,0x278827f6,0xa1649a46,
0x22d71e3e,0x273b27d9,0x255f26a7,0xa5eda472,0x266d2513,0x24c4262f,0x1fc6238b,0xa7c3a70e,0x216425a8,0xa788a5a8,0x1648a21f,0x27fe2764,
0xa41d9a46,0xa6dda7f6,0x266d238b,0x24c4270e,0xa7eaa6a7,0x9cb2a472,0x27c327d9,0x9fc61e3e,0xa5eda7a8,0x255f20a5,0x22d7262f,0xa73ba513,
0x9cb2a5a8,0x27ea25a8,0xa7c3a764,0x1fc6a21f,0x273b238b,0x22d7270e,0x9648a513,0x27fe262f,0x255f27d9,0xa5ed9e3e,0x27882472,0x216426a7,
0xa41d1a46,0xa6dda7f6,0x24c427a8,0xa66da0a5,0x964825a8,0xa7fea5a8,0xa2d7221f,0xa73ba764,0xa7eaa62f,0x1cb2a513,0xa6dda7a8,0x241da0a5,
0x1fc6a472,0x27c326a7,0x24c49e3e,0x266d27d9,0x2788270e,0xa164238b,0x25ed27f6,0xa55f1a46,0x1fc6a5a8,0x27c325a8,0x266d2764,0xa4c4221f,
0x25ed27a8,0xa55f20a5,0xa73b9a46,0xa2d7a7f6,0xa7889e3e,0xa164a7d9,0x1648a6a7,0x27fe2472,0x1cb2a62f,0x27ea2513,0x26dd270e,0xa41d238b,
0xa2d725a8,0xa73ba5a8,0x25eda21f,0x255f2764,0x9fc6a7f6,0x27c31a46,0x9cb2270e,0xa7eaa38b,0x266d26a7,0xa4c42472,0xa41da7d9,0x26dd9e3e,
0xa7fea0a5,0x9648a7a8,0x27882513,0xa164262f,0x24c4a5a8,0x266d25a8,0xa41da764,0x26dda21f,0xa164270e,0xa788a38b,0x25ed262f,0xa55f2513,
0x1648a7d9,0x27fe1e3e,0xa73ba472,0x22d7a6a7,0x1fc627f6,0xa7c31a46,0x27ea20a5,0x9cb227a8,0xa5ed25a8,0xa55fa5a8,0xa788221f,0xa164a764,
0x266da513,0x24c4262f,0x27c3a0a5,0x1fc627a8,0xa6dd2472,0xa41da6a7,0xa7ea1e3e,0x9cb2a7d9,0x273ba38b,0x22d7270e,0x27fe9a46,0x164827f6,
0x26dda5a8,0x241d25a8,0x1cb22764,0xa7ea221f,0xa7fe20a5,0x9648a7a8,0x2164a7f6,0x27881a46,0x273b1e3e,0xa2d727d9,0xa5ed26a7,0xa55fa472,
0xa4c4a513,0x266da62f,0x27c3a38b,0x1fc6270e,0xa78825a8,0xa164a5a8,0x27fea21f,0x96482764,0x26dd1a46,0xa41d27f6,0xa4c4a38b,0x266da70e,
0x9cb2a6a7,0x27eaa472,0x9fc627d9,0xa7c31e3e,0xa55f27a8,0xa5eda0a5,0x273ba62f,0x22d72513,0x27eaa5a8,0x1cb225a8,0x1fc6a764,0x27c3a21f,
0xa2d7a38b,0x273ba70e,0xa7fe2513,0x9648a62f,0xa5ed27d9,0xa55f9e3e,0x21642472,0xa78826a7,0x26dd9a46,0xa41d27f6,0x266da7a8,0x24c420a5,
0xa7fe25a8,0x1648a5a8,0xa73b221f,0x22d7a764,0x9cb2262f,0xa7ea2513,0xa41d27a8,0xa6dd20a5,0x27c3a472,0x9fc626a7,0x266d9e3e,0xa4c427d9,
0x2164a70e,0x2788a38b,0x255fa7f6,0x25ed9a46,0x27c3a5a8,0x9fc625a8,0xa4c42764,0xa66d221f,0x255fa7a8,0x25eda0a5,0x22d71a46,0xa73b27f6,
0xa1649e3e,0x2788a7d9,0x27fea6a7,0x96482472,0xa7ea262f,0x1cb2a513,0x241da70e,0x26dda38b,0xa73b25a8,0x22d7a5a8,0x255fa21f,0xa5ed2764,
0xa7c327f6,0x9fc69a46,0x27eaa70e,0x9cb2238b,0xa4c426a7,0xa66d2472,0x26dda7d9,0x241d9e3e,0x164820a5,0xa7fe27a8,0x2164a513,0x2788a62f,
0x266da5a8,0xa4c425a8,0x26dda764,0x241da21f,0x2788a70e,0xa164238b,0x255fa62f,0x25eda513,0x27fea7d9,0x96481e3e,0x22d7a472,0x273ba6a7,
0x27c3a7f6,0x1fc69a46,0x1cb2a0a5,0x27eaa7a8,0xa55f25a8,0x25eda5a8,0xa164221f,0x2788a764,0xa4c42513,0x266da62f,0x9fc620a5,0x27c3a7a8,
0xa41d2472,0x26dda6a7,0x9cb21e3e,0x27eaa7d9,0xa2d7238b,0x273ba70e,0x96481a46,0x27fea7f6,0x241da5a8,0xa6dd25a8,0xa7ea2764,0x9cb2221f,
0x1648a0a5,0xa7fe27a8,0xa78827f6,0x21649a46,0xa2d71e3e,0xa73b27d9,0xa55f26a7,0x25eda472,0xa66d2513,0xa4c4262f,0x9fc6238b,0x27c3a70e,
0xa16425a8,0x2788a5a8,0x9648a21f,0xa7fe2764,0x241d9a46,0x26dda7f6,0xa66d238b,0xa4c4270e,0x27eaa6a7,0x1cb2a472,0xa7c327d9,0x1fc61e3e,
0x25eda7a8,0xa55f20a5,0xa2d7262f,0x273ba513,0x1cb2a5a8,0xa7ea25a8,0x27c3a764,0x9fc6a21f,0xa73b238b,0xa2d7270e,0x1648a513,0xa7fe262f,
0xa55f27d9,0x25ed9e3e,0xa7882472,0xa16426a7,0x241d1a46,0x26dda7f6,0xa4c427a8,0x266da0a5,0x164825a8,0x27fea5a8,0x22d7221f,0x273ba764,
0x27eaa62f,0x9cb2a513,0x26dda7a8,0xa41da0a5,0x9fc6a472,0xa7c326a7,0xa4c49e3e,0xa66d27d9,0xa788270e,0x2164238b,0xa5ed27f6,0x255f1a46,
0x9fc6a5a8,0xa7c325a8,0xa66d2764,0x24c4221f,0xa5ed27a8,0x255f20a5,0x273b9a46,0x22d7a7f6,0x27889e3e,0x2164a7d9,0x9648a6a7,0xa7fe2472,
0x9cb2a62f,0xa7ea2513,0xa6dd270e,0x241d238b,0x22d725a8,0x273ba5a8,0xa5eda21f,0xa55f2764,0x1fc6a7f6,0xa7c31a46,0x1cb2270e,0x27eaa38b,
0xa66d26a7,0x24c42472,0x241da7d9,0xa6dd9e3e,0x27fea0a5,0x1648a7a8,0xa7882513,0x2164262f,0xa4c4a5a8,0xa66d25a8,0x241da764,0xa6dda21f,
0x2164270e,0x2788a38b,0xa5ed262f,0x255f2513,0x9648a7d9,0xa7fe1e3e,0x273ba472,0xa2d7a6a7,0x9fc627f6,0x27c31a46,0xa7ea20a5,0x1cb227a8,
0x25ed25a8,0x255fa5a8,0x2788221f,0x2164a764,0xa66da513,0xa4c4262f,0xa7c3a0a5,0x9fc627a8,0x26dd2472,0x241da6a7,0x27ea1e3e,0x1cb2a7d9,
0xa73ba38b,0xa2d7270e,0xa7fe9a46,0x964827f6,0xa6dda5a8,0xa41d25a8,0x9cb22764,0x27ea221f,0x27fe20a5,0x1648a7a8,0xa164a7f6,0xa7881a46,
0xa73b1e3e,0x22d727d9,0x25ed26a7,0x255fa472,0x24c4a513,0xa66da62f,0xa7c3a38b,0x9fc6270e,0x278825a8,0x2164a5a8,0xa7fea21f,0x16482764,
0xa6dd1a46,0x241d27f6,0x24c4a38b,0xa66da70e,0x1cb2a6a7,0xa7eaa472,0x1fc627d9,0x27c31e3e,0x255f27a8,0x25eda0a5,0xa73ba62f,0xa2d72513,
0xa7eaa5a8,0x9cb225a8,0x9fc6a764,0xa7c3a21f,0x22d7a38b,0xa73ba70e,0x27fe2513,0x1648a62f,0x25ed27d9,0x255f9e3e,0xa1642472,0x278826a7,
0xa6dd9a46,0x241d27f6,0xa66da7a8,0xa4c420a5,0x27fe25a8,0x9648a5a8,0x273b221f,0xa2d7a764,0x1cb2262f,0x27ea2513,0x241d27a8,0x26dd20a5,
0xa7c3a472,0x1fc626a7,0xa66d9e3e,0x24c427d9,0xa164a70e,0xa788a38b,0xa55fa7f6,0xa5ed9a46,0xa7c3a5a8,0x1fc625a8,0x24c42764,0x266d221f,
0xa55fa7a8,0xa5eda0a5,0xa2d71a46,0x273b27f6,0x21649e3e,0xa788a7d9,0xa7fea6a7,0x16482472,0x27ea262f,0x9cb2a513,0xa41da70e,0xa6dda38b,
0x273b25a8,0xa2d7a5a8,0xa55fa21f,0x25ed2764,0x27c327f6,0x1fc69a46,0xa7eaa70e,0x1cb2238b,0x24c426a7,0x266d2472,0xa6dda7d9,0xa41d9e3e,
0x964820a5,0x27fe27a8,0xa164a513,0xa788a62f,0xa66da5a8,0x24c425a8,0xa6dda764,0xa41da21f,0xa788a70e,0x2164238b,0xa55fa62f,0xa5eda513,
0xa7fea7d9,0x16481e3e,0xa2d7a472,0xa73ba6a7,0xa7c3a7f6,0x9fc69a46,0x9cb2a0a5,0xa7eaa7a8,
};

#define PROF(slot) do {} while (0)
#define PROF3(slot) do {} while (0)
#define PROF2(slot) do {} while (0)

__device__ __forceinline__ uint32_t smem_u32(const void* p) { return (uint32_t)__cvta_generic_to_shared(p); }

__device__ __forceinline__ void mbar_init(uint32_t a, uint32_t c) {
  asm volatile("mbarrier.init.shared::cta.b64 [%0], %1;\n" ::"r"(a), "r"(c) : "memory");
}
__device__ __forceinline__ void mbar_expect_tx(uint32_t a, uint32_t bytes) {
  asm volatile("mbarrier.arrive.expect_tx.shared::cta.b64 _, [%0], %1;\n" ::"r"(a), "r"(bytes) : "memory");
}
__device__ __forceinline__ void mbar_arrive_cluster(uint32_t cluster_addr) {
  asm volatile("mbarrier.arrive.shared::cluster.b64 _, [%0];\n" ::"r"(cluster_addr) : "memory");
}
__device__ __forceinline__ void mbar_arrive_cluster_n(uint32_t cluster_addr, uint32_t n) {
  asm volatile("mbarrier.arrive.shared::cluster.b64 _, [%0], %1;\n" ::"r"(cluster_addr), "r"(n) : "memory");
}
__device__ __forceinline__ bool mbar_try(uint32_t a, uint32_t parity) {
  uint32_t ok;
  asm volatile("{\n.reg .pred p;\nmbarrier.try_wait.parity.shared::cta.b64 p, [%1], %2;\nselp.u32 %0, 1, 0, p;\n}\n"
               : "=r"(ok) : "r"(a), "r"(parity) : "memory");
  return ok;
}
__device__ __forceinline__ void mbar_wait(uint32_t a, uint32_t parity) {
  if (mbar_try(a, parity)) return;
#pragma unroll 1
  for (int n = 0; n < SPIN_LIMIT; n++)
    if (mbar_try(a, parity)) break;
}
__device__ __forceinline__ void mbar_wait_idle(uint32_t a, uint32_t parity) {
#pragma unroll 1
  for (int n = 0; n < SPIN_LIMIT; n++) {
    uint32_t ok;
    asm volatile("{\n.reg .pred p;\nmbarrier.try_wait.parity.shared::cta.b64 p, [%1], %2, %3;\nselp.u32 %0, 1, 0, p;\n}\n"
                 : "=r"(ok) : "r"(a), "r"(parity), "r"(4000) : "memory");
    if (ok) break;
  }
}
__device__ __forceinline__ bool elect_one() {
  uint32_t p;
  asm volatile("{\n.reg .pred P;\nelect.sync _|P, 0xffffffff;\nselp.u32 %0, 1, 0, P;\n}\n" : "=r"(p));
  return p;
}
__device__ __forceinline__ uint32_t mapa(uint32_t a, uint32_t rank) {
  uint32_t r;
  asm volatile("mapa.shared::cluster.u32 %0, %1, %2;\n" : "=r"(r) : "r"(a), "r"(rank));
  return r;
}
__device__ __forceinline__ void nb_sync(int id, int n) { asm volatile("bar.sync %0, %1;\n" ::"r"(id), "r"(n) : "memory"); }
__device__ __forceinline__ void nb_arrive(int id, int n) { asm volatile("bar.arrive %0, %1;\n" ::"r"(id), "r"(n) : "memory"); }
__device__ __forceinline__ void cluster_sync_all() {
  asm volatile("barrier.cluster.arrive.relaxed.aligned;\nbarrier.cluster.wait.aligned;\n" ::: "memory");
}
__device__ __forceinline__ void fence_async_smem() { asm volatile("fence.proxy.async.shared::cta;\n" ::: "memory"); }
__device__ __forceinline__ void fence_async_all() { asm volatile("fence.proxy.async.global;\n" ::: "memory"); }

__device__ __forceinline__ void tma_load_3d(uint32_t dst, const CUtensorMap* tm, uint32_t bar, int c0, int c1, int c2) {
  asm volatile(
      "cp.async.bulk.tensor.3d.shared::cluster.global.mbarrier::complete_tx::bytes [%0], [%1, {%3, %4, %5}], [%2];\n"
      ::"r"(dst), "l"(tm), "r"(bar), "r"(c0), "r"(c1), "r"(c2) : "memory");
}
__device__ __forceinline__ void tma_load_4d(uint32_t dst, const CUtensorMap* tm, uint32_t bar, int c0, int c1, int c2, int c3) {
  asm volatile(
      "cp.async.bulk.tensor.4d.shared::cluster.global.mbarrier::complete_tx::bytes [%0], [%1, {%3, %4, %5, %6}], [%2];\n"
      ::"r"(dst), "l"(tm), "r"(bar), "r"(c0), "r"(c1), "r"(c2), "r"(c3) : "memory");
}
__device__ __forceinline__ void tma_load_3d_mc(uint32_t dst, const CUtensorMap* tm, uint32_t bar, int c0, int c1, int c2) {
  asm volatile(
      "cp.async.bulk.tensor.3d.shared::cluster.global.mbarrier::complete_tx::bytes.multicast::cluster [%0], [%1, {%3, %4, %5}], [%2], %6;\n"
      ::"r"(dst), "l"(tm), "r"(bar), "r"(c0), "r"(c1), "r"(c2), "h"((uint16_t)3) : "memory");
}
__device__ __forceinline__ void tma_load_5d(uint32_t dst, const CUtensorMap* tm, uint32_t bar, int c0, int c4) {
  asm volatile(
      "cp.async.bulk.tensor.5d.shared::cluster.global.mbarrier::complete_tx::bytes [%0], [%1, {%3, %5, %5, %5, %4}], [%2];\n"
      ::"r"(dst), "l"(tm), "r"(bar), "r"(c0), "r"(c4), "r"(0) : "memory");
}
__device__ __forceinline__ void bulk_load(uint32_t dst, const void* src, uint32_t bytes, uint32_t bar) {
  asm volatile("cp.async.bulk.shared::cluster.global.mbarrier::complete_tx::bytes [%0], [%1], %2, [%3];\n"
               ::"r"(dst), "l"(src), "r"(bytes), "r"(bar) : "memory");
}
__device__ __forceinline__ void bulk_commit() { asm volatile("cp.async.bulk.commit_group;\n" ::: "memory"); }
__device__ __forceinline__ void bulk_wait0() { asm volatile("cp.async.bulk.wait_group 0;\n" ::: "memory"); }
__device__ __forceinline__ void prefetch_tmap(const CUtensorMap* tm) {
  asm volatile("prefetch.tensormap [%0];\n" ::"l"(tm) : "memory");
}

__device__ __forceinline__ void wg_fence() { asm volatile("wgmma.fence.sync.aligned;\n" ::: "memory"); }
__device__ __forceinline__ void wg_commit() { asm volatile("wgmma.commit_group.sync.aligned;\n" ::: "memory"); }
template <int N> __device__ __forceinline__ void wg_wait() {
  asm volatile("wgmma.wait_group.sync.aligned %0;\n" ::"n"(N) : "memory");
}
__device__ __forceinline__ uint64_t mkdesc(uint32_t addr, uint32_t lbo, uint32_t sbo, uint32_t swz) {
  return (uint64_t)((addr & 0x3FFFF) >> 4) | ((uint64_t)(lbo >> 4) << 16) | ((uint64_t)(sbo >> 4) << 32) |
         ((uint64_t)swz << 62);
}

#define R4(d, o) "+f"(d[o + 0]), "+f"(d[o + 1]), "+f"(d[o + 2]), "+f"(d[o + 3])
#define R8(d, o) R4(d, o), R4(d, o + 4)
#define R16(d, o) R8(d, o), R8(d, o + 8)
#define R32(d, o) R16(d, o), R16(d, o + 16)
#define R64(d, o) R32(d, o), R32(d, o + 32)

__device__ __forceinline__ void wgmma_n192(float (&d)[96], uint64_t da, uint64_t db, uint32_t acc) {
  asm volatile(
      "{\n.reg .pred p;\nsetp.ne.u32 p, %98, 0;\n"
      "wgmma.mma_async.sync.aligned.m64n192k16.f32.bf16.bf16 "
      "{%0,%1,%2,%3,%4,%5,%6,%7,%8,%9,%10,%11,%12,%13,%14,%15,%16,%17,%18,%19,%20,%21,%22,%23,%24,%25,%26,%27,%28,%29,%30,%31,"
      "%32,%33,%34,%35,%36,%37,%38,%39,%40,%41,%42,%43,%44,%45,%46,%47,%48,%49,%50,%51,%52,%53,%54,%55,%56,%57,%58,%59,%60,%61,%62,%63,"
      "%64,%65,%66,%67,%68,%69,%70,%71,%72,%73,%74,%75,%76,%77,%78,%79,%80,%81,%82,%83,%84,%85,%86,%87,%88,%89,%90,%91,%92,%93,%94,%95}, "
      "%96, %97, p, 1, 1, 0, 1;\n}\n"
      : R64(d, 0), R32(d, 64)
      : "l"(da), "l"(db), "r"(acc));
}
__device__ __forceinline__ void wgmma_n128(float (&d)[64], uint64_t da, uint64_t db, uint32_t acc) {
  asm volatile(
      "{\n.reg .pred p;\nsetp.ne.u32 p, %66, 0;\n"
      "wgmma.mma_async.sync.aligned.m64n128k16.f32.bf16.bf16 "
      "{%0,%1,%2,%3,%4,%5,%6,%7,%8,%9,%10,%11,%12,%13,%14,%15,%16,%17,%18,%19,%20,%21,%22,%23,%24,%25,%26,%27,%28,%29,%30,%31,"
      "%32,%33,%34,%35,%36,%37,%38,%39,%40,%41,%42,%43,%44,%45,%46,%47,%48,%49,%50,%51,%52,%53,%54,%55,%56,%57,%58,%59,%60,%61,%62,%63}, "
      "%64, %65, p, 1, 1, 0, 1;\n}\n"
      : R64(d, 0)
      : "l"(da), "l"(db), "r"(acc));
}
template <int N> __device__ __forceinline__ void fence_regs(float (&d)[N]) {
#pragma unroll
  for (int i = 0; i < N; i++) asm volatile("" : "+f"(d[i])::"memory");
}

__device__ __forceinline__ void mma16816(float (&d)[4], uint32_t a0, uint32_t a1, uint32_t a2, uint32_t a3, uint32_t b0,
                                         uint32_t b1) {
  asm("mma.sync.aligned.m16n8k16.row.col.f32.bf16.bf16.f32 {%0,%1,%2,%3}, {%4,%5,%6,%7}, {%8,%9}, {%0,%1,%2,%3};\n"
      : "+f"(d[0]), "+f"(d[1]), "+f"(d[2]), "+f"(d[3])
      : "r"(a0), "r"(a1), "r"(a2), "r"(a3), "r"(b0), "r"(b1));
}
__device__ __forceinline__ void mma16816_z(float (&d)[4], uint32_t a0, uint32_t a1, uint32_t a2, uint32_t a3, uint32_t b0,
                                           uint32_t b1) {
  asm("mma.sync.aligned.m16n8k16.row.col.f32.bf16.bf16.f32 {%0,%1,%2,%3}, {%4,%5,%6,%7}, {%8,%9}, {%10,%10,%10,%10};\n"
      : "=f"(d[0]), "=f"(d[1]), "=f"(d[2]), "=f"(d[3])
      : "r"(a0), "r"(a1), "r"(a2), "r"(a3), "r"(b0), "r"(b1), "f"(0.f));
}
__device__ __forceinline__ void ldsm4t(uint32_t (&r)[4], uint32_t a) {
  asm volatile("ldmatrix.sync.aligned.m8n8.x4.trans.shared.b16 {%0,%1,%2,%3}, [%4];\n"
               : "=r"(r[0]), "=r"(r[1]), "=r"(r[2]), "=r"(r[3]) : "r"(a) : "memory");
}
__device__ __forceinline__ void ldsm2t(uint32_t& r0, uint32_t& r1, uint32_t a) {
  asm volatile("ldmatrix.sync.aligned.m8n8.x2.trans.shared.b16 {%0,%1}, [%2];\n" : "=r"(r0), "=r"(r1) : "r"(a) : "memory");
}
__device__ __forceinline__ void st_async128(uint32_t a, uint32_t bar, uint32_t x, uint32_t y, uint32_t z, uint32_t w) {
  asm volatile("st.async.weak.shared::cluster.mbarrier::complete_tx::bytes.v4.b32 [%0], {%2,%3,%4,%5}, [%1];\n"
               ::"r"(a), "r"(bar), "r"(x), "r"(y), "r"(z), "r"(w) : "memory");
}
__device__ __forceinline__ void mbar_arrive(uint32_t a) {
  asm volatile("mbarrier.arrive.shared::cta.b64 _, [%0];\n" ::"r"(a) : "memory");
}
__device__ __forceinline__ void stsm4(uint32_t a, uint32_t r0, uint32_t r1, uint32_t r2, uint32_t r3) {
  asm volatile("stmatrix.sync.aligned.m8n8.x4.shared.b16 [%0], {%1,%2,%3,%4};\n"
               ::"r"(a), "r"(r0), "r"(r1), "r"(r2), "r"(r3) : "memory");
}
__device__ __forceinline__ void stsm4t(uint32_t a, uint32_t r0, uint32_t r1, uint32_t r2, uint32_t r3) {
  asm volatile("stmatrix.sync.aligned.m8n8.x4.trans.shared.b16 [%0], {%1,%2,%3,%4};\n"
               ::"r"(a), "r"(r0), "r"(r1), "r"(r2), "r"(r3) : "memory");
}
__device__ __forceinline__ uint2 lds64(uint32_t a) {
  uint2 v;
  asm volatile("ld.shared.v2.u32 {%0,%1}, [%2];\n" : "=r"(v.x), "=r"(v.y) : "r"(a));
  return v;
}
__device__ __forceinline__ uint4 lds128(uint32_t a) {
  uint4 v;
  asm volatile("ld.shared.v4.u32 {%0,%1,%2,%3}, [%4];\n" : "=r"(v.x), "=r"(v.y), "=r"(v.z), "=r"(v.w) : "r"(a) : "memory");
  return v;
}
__device__ __forceinline__ void sts128(uint32_t a, uint32_t x, uint32_t y, uint32_t z, uint32_t w) {
  asm volatile("st.shared.v4.u32 [%0], {%1,%2,%3,%4};\n" ::"r"(a), "r"(x), "r"(y), "r"(z), "r"(w) : "memory");
}
__device__ __forceinline__ uint32_t pack_bf16(float lo, float hi) {
  uint32_t r;
  asm("cvt.rn.bf16x2.f32 %0, %1, %2;\n" : "=r"(r) : "f"(hi), "f"(lo));
  return r;
}
__device__ __forceinline__ uint32_t bmul2(uint32_t a, uint32_t b) {
  uint32_t r;
  asm("mul.rn.bf16x2 %0, %1, %2;\n" : "=r"(r) : "r"(a), "r"(b));
  return r;
}
__device__ __forceinline__ uint32_t bmax2(uint32_t a, uint32_t b) {
  uint32_t r;
  asm("max.bf16x2 %0, %1, %2;\n" : "=r"(r) : "r"(a), "r"(b));
  return r;
}
__device__ __forceinline__ uint32_t bfma2(uint32_t a, uint32_t b, uint32_t c) {
  uint32_t r;
  asm("fma.rn.bf16x2 %0, %1, %2, %3;\n" : "=r"(r) : "r"(a), "r"(b), "r"(c));
  return r;
}
__device__ __forceinline__ uint32_t badd2(uint32_t a, uint32_t b) {
  uint32_t r;
  asm("add.rn.bf16x2 %0, %1, %2;\n" : "=r"(r) : "r"(a), "r"(b));
  return r;
}
__device__ __forceinline__ void prefetch_l2(const void* p) { asm volatile("prefetch.global.L2 [%0];\n" ::"l"(p)); }
__device__ __forceinline__ void cp_async16n(uint32_t dst, const void* src) {
  asm volatile("cp.async.cg.shared.global [%0], [%1], 16;\n" ::"r"(dst), "l"(src) : "memory");
}
__device__ __forceinline__ void cp_async16(uint32_t dst, const void* src, uint32_t srcbytes) {
  asm volatile("cp.async.cg.shared.global.L2::256B [%0], [%1], 16, %2;\n" ::"r"(dst), "l"(src), "r"(srcbytes) : "memory");
}
__device__ __forceinline__ uint32_t ld_acquire(const uint32_t* p) {
  uint32_t v;
  asm volatile("ld.acquire.gpu.global.u32 %0, [%1];\n" : "=r"(v) : "l"(p) : "memory");
  return v;
}
__device__ __forceinline__ uint32_t ld_relaxed(const uint32_t* p) {
  uint32_t v;
  asm volatile("ld.relaxed.gpu.global.u32 %0, [%1];\n" : "=r"(v) : "l"(p) : "memory");
  return v;
}
__device__ __forceinline__ void st_release(uint32_t* p, uint32_t v) {
  asm volatile("st.release.gpu.global.u32 [%0], %1;\n" ::"l"(p), "r"(v) : "memory");
}
__device__ __forceinline__ void wait_flag(const uint32_t* p, uint32_t want) {
  int n = 0;
  while (ld_relaxed(p) != want && ++n < SPIN_LIMIT) __nanosleep(40);
  (void)ld_acquire(p);
}

struct Params {
  const __nv_bfloat16* x;
  const __nv_bfloat16* w;
  const __nv_bfloat16* q;
  const __nv_bfloat16* k;
  const __nv_bfloat16* v;
  const __nv_bfloat16* shift_k;
  const __nv_bfloat16* ssm_k;
  const __nv_bfloat16* ssm_D;
  const __nv_bfloat16* wo;
  __nv_bfloat16* out;
};

__device__ __forceinline__ uint32_t lds32(uint32_t a) {
  uint32_t v;
  asm volatile("ld.shared.u32 %0, [%1];\n" : "=r"(v) : "r"(a));
  return v;
}
#define W4(d, o) "=f"(d[o + 0]), "=f"(d[o + 1]), "=f"(d[o + 2]), "=f"(d[o + 3])
#define W8(d, o) W4(d, o), W4(d, o + 4)
#define W16(d, o) W8(d, o), W8(d, o + 8)
#define U4(c, d, o) c(d[o + 0]), c(d[o + 1]), c(d[o + 2]), c(d[o + 3])
#define U8(c, d, o) U4(c, d, o), U4(c, d, o + 4)
#define U16(c, d, o) U8(c, d, o), U8(c, d, o + 8)
#define U32(c, d, o) U16(c, d, o), U16(c, d, o + 16)
#define D32 "{%0,%1,%2,%3,%4,%5,%6,%7,%8,%9,%10,%11,%12,%13,%14,%15,%16,%17,%18,%19,%20,%21,%22,%23,%24,%25,%26,%27,%28,%29,%30,%31}"
#define D16 "{%0,%1,%2,%3,%4,%5,%6,%7,%8,%9,%10,%11,%12,%13,%14,%15}"
#define D8 "{%0,%1,%2,%3,%4,%5,%6,%7}"
template <int ACC> __device__ __forceinline__ void hmma_n128t(uint32_t (&d)[32], const uint32_t (&a)[4], uint64_t db) {
  if (ACC)
    asm volatile("wgmma.mma_async.sync.aligned.m64n128k16.f16.f16.f16 " D32 ", {%32,%33,%34,%35}, %36, 1, 1, 1, 1;\n"
                 : U32("+r", d, 0) : "r"(a[0]), "r"(a[1]), "r"(a[2]), "r"(a[3]), "l"(db));
  else
    asm volatile("wgmma.mma_async.sync.aligned.m64n128k16.f16.f16.f16 " D32 ", {%32,%33,%34,%35}, %36, 0, 1, 1, 1;\n"
                 : U32("=r", d, 0) : "r"(a[0]), "r"(a[1]), "r"(a[2]), "r"(a[3]), "l"(db));
}
template <int ACC, int TB> __device__ __forceinline__ void hmma_n32(uint32_t (&d)[8], const uint32_t (&a)[4], uint64_t db) {
  if (ACC)
    asm volatile("wgmma.mma_async.sync.aligned.m64n32k16.f16.f16.f16 " D8 ", {%8,%9,%10,%11}, %12, 1, 1, 1, %13;\n"
                 : U8("+r", d, 0) : "r"(a[0]), "r"(a[1]), "r"(a[2]), "r"(a[3]), "l"(db), "n"(TB));
  else
    asm volatile("wgmma.mma_async.sync.aligned.m64n32k16.f16.f16.f16 " D8 ", {%8,%9,%10,%11}, %12, 0, 1, 1, %13;\n"
                 : U8("=r", d, 0) : "r"(a[0]), "r"(a[1]), "r"(a[2]), "r"(a[3]), "l"(db), "n"(TB));
}
template <int N> __device__ __forceinline__ void fence_regs(uint32_t (&d)[N]) {
#pragma unroll
  for (int i = 0; i < N; i++) asm volatile("" : "+r"(d[i])::"memory");
}
__device__ __forceinline__ uint32_t hmul(uint32_t a, uint32_t b) { uint32_t r; asm("mul.rn.f16x2 %0, %1, %2;\n" : "=r"(r) : "r"(a), "r"(b)); return r; }
__device__ __forceinline__ uint32_t hadd(uint32_t a, uint32_t b) { uint32_t r; asm("add.rn.f16x2 %0, %1, %2;\n" : "=r"(r) : "r"(a), "r"(b)); return r; }
__device__ __forceinline__ uint32_t hsub(uint32_t a, uint32_t b) { uint32_t r; asm("sub.rn.f16x2 %0, %1, %2;\n" : "=r"(r) : "r"(a), "r"(b)); return r; }
__device__ __forceinline__ uint32_t hfma(uint32_t a, uint32_t b, uint32_t c) { uint32_t r; asm("fma.rn.f16x2 %0, %1, %2, %3;\n" : "=r"(r) : "r"(a), "r"(b), "r"(c)); return r; }
__device__ __forceinline__ uint32_t hfnma(uint32_t a, uint32_t b, uint32_t c) {
  uint32_t r;
  asm("{\n.reg .b32 t;\nneg.f16x2 t, %1;\nfma.rn.f16x2 %0, t, %2, %3;\n}\n" : "=r"(r) : "r"(a), "r"(b), "r"(c));
  return r;
}
__device__ __forceinline__ uint32_t hrefl(uint32_t p, uint32_t s) {
  uint32_t r;
  asm("{\n.reg .b32 t;\nneg.f16x2 t, %2;\nfma.rn.f16x2 %0, %1, %3, t;\n}\n" : "=r"(r) : "r"(p), "r"(s), "r"(0x40004000u));
  return r;
}
__device__ __forceinline__ void bfly(uint32_t xr, uint32_t xi, uint32_t tr, uint32_t ti, uint32_t yr, uint32_t yi, uint32_t ur,
                                     uint32_t ui, uint32_t& sr, uint32_t& si, uint32_t& dr, uint32_t& di) {
  const uint32_t pr = hfnma(xi, ti, hmul(xr, tr)), pi = hfma(xi, tr, hmul(xr, ti));
  sr = hfnma(yi, ui, hfma(yr, ur, pr));
  si = hfma(yi, ur, hfma(yr, ui, pi));
  dr = hrefl(pr, sr);
  di = hrefl(pi, si);
}
template <int BH> __device__ __forceinline__ void fft_e1(const uint32_t (&d)[32], const uint32_t (&tw)[16], uint32_t (&a2)[2][2][4]) {
#pragma unroll
  for (int be = 0; be < 2; be++)
#pragma unroll
    for (int s = 0; s < 2; s++) {
      const int o = 16 * s + 8 * be + 2 * BH, p = 2 * BH;
      bfly(d[o], d[o + 1], tw[p], tw[p + 1], d[o + 4], d[o + 5], tw[p + 4], tw[p + 5], a2[be][0][s], a2[be][0][2 + s],
           a2[be][1][s], a2[be][1][2 + s]);
    }
}
__device__ __forceinline__ uint32_t hfms(uint32_t a, uint32_t b, uint32_t c) {
  uint32_t r;
  asm("{\n.reg .b32 t;\nneg.f16x2 t, %3;\nfma.rn.f16x2 %0, %1, %2, t;\n}\n" : "=r"(r) : "r"(a), "r"(b), "r"(c));
  return r;
}
template <int C, int J> __device__ __forceinline__ void fft_e2(const uint32_t (&d0)[8], const uint32_t (&d1)[8], uint32_t (&a3)[2][4]) {
  const uint32_t ur = d0[2 * J], ui = d0[4 + 2 * J], hr = d0[2 * J + 1], hi = d0[5 + 2 * J];
  const uint32_t vr = d1[2 * J], vi = d1[4 + 2 * J], gr = d1[2 * J + 1], gi = d1[5 + 2 * J];
  const uint32_t pr = hfnma(ui, hi, hmul(ur, hr)), pi = hfma(ui, hr, hmul(ur, hi));
  a3[0][2 + C] = pr;
  a3[0][C] = pi;
  a3[1][2 + C] = hfnma(vi, hi, hfma(vr, hr, hfnma(ui, gi, hfms(ur, gr, pi))));
  a3[1][C] = hfma(vi, hr, hfma(vr, hi, hfma(ui, gr, hfma(ur, gi, pr))));
}
__device__ __forceinline__ void fft_e3(const uint32_t (&d)[2][8], const uint32_t (&tw)[16], uint32_t zaddr) {
#pragma unroll
  for (int rho = 0; rho < 2; rho++) {
    uint32_t zr[4], zi[4];
#pragma unroll
    for (int nb = 0; nb < 4; nb++) {
      const uint32_t xi = d[nb >> 1][2 * (nb & 1) + rho], xr = d[nb >> 1][4 + 2 * (nb & 1) + rho];
      const uint32_t tr = tw[8 + 4 * rho + 2 * (nb & 1)], ti = tw[9 + 4 * rho + 2 * (nb & 1)];
      zr[nb] = hfnma(xi, ti, hmul(xr, tr));
      zi[nb] = hfma(xi, tr, hmul(xr, ti));
    }
    stsm4(zaddr + rho * 1024, zr[0], zr[1], zr[2], zr[3]);
    stsm4(zaddr + rho * 1024 + 512, zi[0], zi[1], zi[2], zi[3]);
  }
}
__device__ __forceinline__ float bf_lo(uint32_t v) {
  uint32_t r;
  asm("prmt.b32 %0, %1, 0, 0x1044;\n" : "=r"(r) : "r"(v));
  return __uint_as_float(r);
}
__device__ __forceinline__ float bf_hi(uint32_t v) { return __uint_as_float(v & 0xffff0000u); }
__device__ __forceinline__ float ex2(float x) {
  float r;
  asm("ex2.approx.ftz.f32 %0, %1;\n" : "=f"(r) : "f"(x));
  return r;
}
__device__ __forceinline__ float rcp(float x) {
  float r;
  asm("rcp.approx.ftz.f32 %0, %1;\n" : "=f"(r) : "f"(x));
  return r;
}

__device__ __forceinline__ int g2_a(int s) { return ((0xA1054 >> (4 * s)) & 15) * 16384; }
__device__ __forceinline__ int g2_b(int s) { return ((0xCDB32 >> (4 * s)) & 15) * 16384; }
static_assert(OFF_U == 10 * 16384 && OFF_H == 12 * 16384 && OFF_OP == 4 * 16384, "units");
__device__ __forceinline__ int g2_k(int hp, int i) {
  return i < 2 ? hp ^ 1 ^ i : i < 4 ? (hp & ~1) ^ i : ((hp & ~3) + i) & 15; }
__device__ __forceinline__ int y_slot(int wg, int it) {
  static_assert(T_B2 == T_TW + 8192 && T_A1 == T_B2 + 4096, "y slots");
  return OFF_T + T_TW + ((it + 3) & 3) * 4096 + wg * 2048;
}

__device__ __forceinline__ void to_arr(uint32_t (&d)[4], uint4 v) { d[0] = v.x; d[1] = v.y; d[2] = v.z; d[3] = v.w; }

__device__ __forceinline__ void attn_stage(uint32_t sb, int blk, int lane, const float (&acc)[96], uint32_t (&k1)[2][4]) {
  const int lr = lane & 7, lm = lane >> 3;
  const uint32_t base = sb + OFF_VP + (blk * 16 + lr + 8 * (lm & 1)) * 128;
#pragma unroll
  for (int i = 0; i < 8; i++) k1[i >> 2][i & 3] = pack_bf16(acc[34 + 4 * i], acc[35 + 4 * i]);
  const uint32_t kh = sb + OFF_KH + blk * 2048 + lane * 16;
  sts128(kh, k1[0][0], k1[0][1], k1[0][2], k1[0][3]);
  sts128(kh + 512, k1[1][0], k1[1][1], k1[1][2], k1[1][3]);
#pragma unroll
  for (int j = 0; j < 8; j += 2)
    stsm4(base + (((j + (lm >> 1)) ^ lr) << 4), pack_bf16(acc[64 + 4 * j], acc[65 + 4 * j]),
          pack_bf16(acc[66 + 4 * j], acc[67 + 4 * j]), pack_bf16(acc[68 + 4 * j], acc[69 + 4 * j]),
          pack_bf16(acc[70 + 4 * j], acc[71 + 4 * j]));
}
__device__ __forceinline__ void attn_pack(const float (&acc)[96], uint32_t (&qa)[2][8], uint32_t (&k0)[2][4]) {
#pragma unroll
  for (int hd = 0; hd < 2; hd++) {
#pragma unroll
    for (int i = 0; i < 8; i++) {
      asm volatile("cvt.rn.bf16x2.f32 %0, %1, %2;\n" : "=r"(qa[hd][i]) : "f"(acc[16 * hd + 2 * i + 1]), "f"(acc[16 * hd + 2 * i]));
    }
#pragma unroll
    for (int i = 0; i < 4; i++) {
      asm volatile("cvt.rn.bf16x2.f32 %0, %1, %2;\n" : "=r"(k0[hd][i]) : "f"(acc[33 + 16 * hd + 4 * i]), "f"(acc[32 + 16 * hd + 4 * i]));
    }
  }
}
__device__ __forceinline__ void attn_own(const uint32_t (&k0)[2][4], const uint32_t (&k1)[2][4], bool le0, bool le1,
                                         const uint32_t (&qa)[2][8], float (&l)[2][4]) {
#pragma unroll
  for (int hd = 0; hd < 2; hd++) {
    float s0[4], s1[4];
    mma16816_z(s0, qa[hd][0], qa[hd][1], qa[hd][2], qa[hd][3], k0[hd][0], k0[hd][1]);
    mma16816_z(s1, qa[hd][0], qa[hd][1], qa[hd][2], qa[hd][3], k1[hd][0], k1[hd][1]);
    mma16816(s0, qa[hd][4], qa[hd][5], qa[hd][6], qa[hd][7], k0[hd][2], k0[hd][3]);
    mma16816(s1, qa[hd][4], qa[hd][5], qa[hd][6], qa[hd][7], k1[hd][2], k1[hd][3]);
    l[hd][0] = s0[0];
    l[hd][1] = s0[1];
    l[hd][2] = le0 ? s1[2] : s0[2];
    l[hd][3] = le1 ? s1[3] : s0[3];
  }
}
template <int N> __device__ __forceinline__ void quad_softmax(float (&x)[N][2], uint32_t (&pp)[N]) {
  const float c2 = 1.4426950408889634f;
  uint32_t q[N], mx[N / 2];
#pragma unroll
  for (int n = 0; n < N; n++) {
    const uint32_t r = pack_bf16(x[n][0], x[n][1]);
    q[n] = bfma2(r, 0x3e353e35u, bmul2(r, 0x379e379eu));
    x[n][0] = bf_lo(q[n]);
    x[n][1] = bf_hi(q[n]);
  }
#pragma unroll
  for (int n = 0; n < N / 2; n++)
    mx[n] = bmax2(__byte_perm(q[2 * n], q[2 * n + 1], 0x5410), __byte_perm(q[2 * n], q[2 * n + 1], 0x7632));
#pragma unroll
  for (int o = 1; o <= 2; o++)
#pragma unroll
    for (int n = 0; n < N / 2; n++) mx[n] = bmax2(mx[n], __shfl_xor_sync(0xffffffffu, mx[n], o));
  float m[N], t[N];
#pragma unroll
  for (int n = 0; n < N / 2; n++) {
    m[2 * n] = bf_lo(mx[n]);
    m[2 * n + 1] = bf_hi(mx[n]);
  }
#pragma unroll
  for (int n = 0; n < N; n++) {
    const float nm = -m[n] * c2;
    x[n][0] = ex2(fmaf(x[n][0], c2, nm));
    x[n][1] = ex2(fmaf(x[n][1], c2, nm));
    t[n] = x[n][0] + x[n][1];
  }
#pragma unroll
  for (int o = 1; o <= 2; o++)
#pragma unroll
    for (int n = 0; n < N; n++) t[n] += __shfl_xor_sync(0xffffffffu, t[n], o);
#pragma unroll
  for (int n = 0; n < N; n++) {
    const float inv = rcp(t[n]);
    pp[n] = pack_bf16(x[n][0] * inv, x[n][1] * inv);
  }
}
__device__ __forceinline__ void attn_pv(uint32_t dst, const uint32_t (&va)[4], const uint32_t (&vb)[4], uint32_t pp,
                                        uint32_t maskLE) {
  const uint32_t b0 = pp & ~maskLE, b1 = pp & maskLE;
  float oa[4], ob[4];
  mma16816_z(oa, va[0], va[1], va[2], va[3], b0, b1);
  mma16816_z(ob, vb[0], vb[1], vb[2], vb[3], b0, b1);
  stsm4t(dst, pack_bf16(oa[0], oa[1]), pack_bf16(oa[2], oa[3]), pack_bf16(ob[0], ob[1]), pack_bf16(ob[2], ob[3]));
}

template <int MODE>
__global__ void __cluster_dims__(2, 1, 1) __launch_bounds__(NTHREADS, 1)
fused_kernel(const Params p, const __grid_constant__ CUtensorMap tmX, const __grid_constant__ CUtensorMap tmW,
             const __grid_constant__ CUtensorMap tmWo,
             const __grid_constant__ CUtensorMap tmQ,
             const __grid_constant__ CUtensorMap tmXh, const __grid_constant__ CUtensorMap tmWh) {
  extern __shared__ __align__(1024) uint8_t smem[];
  const uint32_t sb = smem_u32(smem);
  const uint32_t bars = sb + OFF_BAR;
  const int tid = threadIdx.x, lane = tid & 31, warp = __shfl_sync(0xffffffffu, tid >> 5, 0);
  const int rank = blockIdx.x & 1;
  const bool halo_cta = blockIdx.x < 4;
  if (halo_cta && MODE != 0) return;
  int grp, mem;
  {
    const int t = (blockIdx.x >> 1) - 4, u = t - 32;
    const int q7 = (u * 37) >> 8;
    const bool lo = (unsigned)t < 32u, mid = (unsigned)u < 28u;
    grp = lo ? (t & 7) : (mid ? 1 + u - 7 * q7 : 0);
    mem = lo ? (t >> 3) : (mid ? 4 + q7 : (t < 0 ? t + 6 : t - 54));
  }
  const int rg = (grp >> 2) * 4 + (mem >> 1), hp = (grp & 3) * 4 + (mem & 1) * 2 + rank;
  const int rb2 = (grp >> 2) * 8 + mem, cb2 = (grp & 3) * 2 + rank;
  const int chb = grp * 16 + mem * 2 + rank;
  const int cta = rg * 16 + hp;
  const int par = rg >> 2, gidx = rg & 3;

  if (tid < 256 && !halo_cta && MODE != 2) {
    const int r = tid >> 3, c = tid & 7;
    const uint32_t so = r * 128 + ((c ^ (r & 7)) << 4);
    const __nv_bfloat16* wg0 = p.w + (size_t)r * (3 * DM) + hp * 64 + c * 8;
    const __nv_bfloat16* xg0 = p.x + (size_t)(2 * (gidx * 256 + r) + par) * DM + c * 8;
#pragma unroll
    for (int j = 0; j < 3; j++) cp_async16n(sb + OFF_1B + j * 4096 + so, wg0 + j * DM);
#pragma unroll
    for (int i = 0; i < 8; i++) cp_async16n(sb + i * 4096 + so, xg0 + (size_t)i * 64 * DM);
    asm volatile("cp.async.commit_group;\n" ::: "memory");
  }
  if (tid == 256) {
    prefetch_tmap(halo_cta ? &tmXh : &tmX);
#pragma unroll
    for (int i = 0; i < NS1B; i++) mbar_init(bars + 8 * (BAR_FULLB + i), 1);
#pragma unroll
    for (int i = 0; i < NS1A; i++) mbar_init(bars + 8 * (BAR_FULLA + i), 1);
    asm volatile("fence.mbarrier_init.release.cluster;\n" ::: "memory");
    if (!halo_cta && MODE != 2) {
      mbar_expect_tx(bars + 8 * (BAR_FULLB + 1), STG1B);
      tma_load_3d(sb + OFF_1B + 1 * STG1B, &tmW, bars + 8 * (BAR_FULLB + 1), hp * 64, 32, 0);
      mbar_expect_tx(bars + 8 * (BAR_FULLB + 2), STG1B);
      tma_load_3d(sb + OFF_1B + 2 * STG1B, &tmW, bars + 8 * (BAR_FULLB + 2), hp * 64, 64, 0);
    } else {
      prefetch_tmap(&tmWh);
    }
  } else if (tid == 288) {
#pragma unroll
    for (int i = 0; i < NS1A; i++) mbar_init(bars + 8 * (BAR_EMPTYA + i), 4);
#pragma unroll
    for (int i = 0; i < NS1B; i++) mbar_init(bars + 8 * (BAR_EMPTYB + i), 2);
    asm volatile("fence.mbarrier_init.release.cluster;\n" ::: "memory");
  } else if (tid == 320) {
#pragma unroll
    for (int i = 0; i < NS2; i++) {
      mbar_init(bars + 8 * (BAR_FULL2 + i), 1);
      mbar_init(bars + 8 * (BAR_EMPTY2 + i), 4);
    }
    mbar_init(bars + 8 * BAR_DEAD, 2);
    mbar_init(bars + 8 * (BAR_DEAD + 1), 2);
    mbar_init(bars + 8 * BAR_X, 2);
    mbar_init(bars + 8 * BAR_REL, WAVE ? 1 : 2);
    asm volatile("fence.mbarrier_init.release.cluster;\n" ::: "memory");
  } else if (tid == 352) {
    mbar_init(bars + 8 * BAR_T, 1);
    mbar_init(bars + 8 * BAR_UH, 3);
    mbar_init(bars + 8 * BAR_LFREE, 4);
    mbar_init(bars + 8 * BAR_LAND, 1);
    mbar_init(bars + 8 * BAR_U, 1);
    mbar_init(bars + 8 * BAR_Q, 1);
    mbar_init(bars + 8 * BAR_STG, 9);
    asm volatile("fence.mbarrier_init.release.cluster;\n" ::: "memory");
  }
  if (warp == 8) PROF2(23);
  cluster_sync_all();
  if (warp == 8) PROF2(24);

  if (warp >= 8) {
    const int hw = warp - 8;
    const int lr = lane & 7, lm = lane >> 3;
    auto g1_issue_a = [&](int j, int s) {
      const uint32_t fb = bars + 8 * (BAR_FULLA + s);
      mbar_expect_tx(fb, STG1A);
      tma_load_3d_mc(sb + s * STG1A + rank * 16384, &tmX, fb, j * 64, par, gidx * 256 + rank * 128);
    };
    auto g1_issue_b = [&](int kb, int s) {
      const uint32_t fb = bars + 8 * (BAR_FULLB + s);
      mbar_expect_tx(fb, STG1B);
      tma_load_3d(sb + OFF_1B + s * STG1B, &tmW, fb, hp * 64, kb * 32, 0);
    };
    asm volatile("setmaxnreg.dec.sync.aligned.u32 %0;\n" :: "n"(REG_HELP));

    if (halo_cta) {
      if (hw == 0) {
        int s = 0, ph = 1;
#pragma unroll 1
        for (int kb = 0; kb < 16; kb++) {
          mbar_wait(bars + 8 * (BAR_EMPTYB + s), ph);
          const uint32_t fb = bars + 8 * (BAR_FULLB + s), st = sb + s * STGH;
          if (elect_one()) {
            mbar_expect_tx(fb, STGH);
            tma_load_4d(st, &tmXh, fb, kb * 64, 248, 0, 0);
            tma_load_3d(st + 8192, &tmWh, fb, 0, kb * 64, 16 + blockIdx.x * 4);
            tma_load_3d(st + 8192 + 32768, &tmWh, fb, 0, kb * 64, 32 + blockIdx.x * 4);
          }
          if (++s == 3) { s = 0; ph ^= 1; }
        }
      }
      __syncwarp();
    } else if (hw == 0) {
      uint32_t epoch = 0;
      if (lane < (MODE == 2 ? NS2 : 2)) mbar_arrive_cluster_n(mapa(bars, rank) + 8 * (BAR_EMPTY2 + lane), 4);
      if (MODE != 2) {
      epoch = ld_relaxed(g_flag_o + 2 * cta) + 1;
      if (lane == 0) {
        mbar_expect_tx(bars + 8 * BAR_U, 32768);
        mbar_expect_tx(bars + 8 * BAR_LAND, 32768 + 64);
        mbar_expect_tx(bars + 8 * BAR_Q, 32768);
        mbar_expect_tx(bars + 8 * BAR_T, T_END);
      }
      {
        int sa = 1, pha = 1, sbb = 2, phb = 1;
#pragma unroll 1
        for (int kb = 2; kb < 32; kb++) {
          if (!(kb & 1)) {
            mbar_wait(bars + 8 * (BAR_EMPTYA + sa), pha);
            if (elect_one()) g1_issue_a(kb >> 1, sa);
            if (++sa == NS1A) { sa = 0; pha ^= 1; }
          }
          mbar_wait(bars + 8 * (BAR_EMPTYB + sbb), phb);
          if (kb > 2 && elect_one()) g1_issue_b(kb, sbb);
          __syncwarp();
          if (kb >= PF0 && kb < PF0 + 12)
            prefetch_l2((kb < PF0 + 8 ? p.q + (size_t)chb * 16384 + (kb - PF0) * 2048 : p.wo + (size_t)chb * 8192 + (kb - PF0 - 8) * 2048) + lane * 64);
          if (kb == 4) PROF2(27);
          if (kb == 1) PROF2(38);
          if (kb == 2) PROF2(39);
          if (++sbb == NS1B) { sbb = 0; phb ^= 1; }
        }
      }
      static_assert(32 % NS1B == 2 && (32 / NS1B) % 2 == 0 && OFF_Q == OFF_1B && 2 * STG1B == 6 * 4096, "slots / parity of these loads");
      const uint8_t* tab = reinterpret_cast<const uint8_t*>(g_tab);
      if (lane == 0) {
        prefetch_tmap(&tmWo);
        prefetch_tmap(&tmQ);
        bulk_load(sb + OFF_T + T_A1, tab + T_A1, T_END - T_A1, bars + 8 * BAR_T);
        mbar_wait(bars + 8 * (BAR_EMPTYB + 2), 1);
        tma_load_5d(sb + OFF_Q + 6 * 4096, &tmQ, bars + 8 * BAR_Q, (chb & ~1) * 8, rank * 32 + 24);
        tma_load_5d(sb + OFF_Q + 7 * 4096, &tmQ, bars + 8 * BAR_Q, (chb & ~1) * 8, rank * 32 + 28);
        if (gidx != 0) wait_flag(g_flag_h + (hp >> 2), epoch);
      }
      __syncwarp();
      {
        uint4 hk0 = make_uint4(0, 0, 0, 0), hk1 = hk0, hv0 = hk0, hv1 = hk0;
        if (gidx != 0) {
          const uint4* src = g_halo + cta * 128 + lane;
          hk0 = __ldcg(src); hk1 = __ldcg(src + 32); hv0 = __ldcg(src + 64); hv1 = __ldcg(src + 96);
        }
        if (lane == 0) {
          mbar_wait(bars + 8 * (BAR_EMPTYB + 3), 1);
          bulk_load(sb + OFF_T, tab, T_TW, bars + 8 * BAR_T);
        }
        __syncwarp();
        PROF2(18);
        sts128(sb + OFF_L0 + 1024 + lane * 16, hk0.x, hk0.y, hk0.z, hk0.w);
        sts128(sb + OFF_L0 + 1536 + lane * 16, hk1.x, hk1.y, hk1.z, hk1.w);
        stsm4(sb + OFF_L0 + lr * 128 + ((lm ^ lr) << 4), hv0.x, hv0.y, hv0.z, hv0.w);
        stsm4(sb + OFF_L0 + lr * 128 + (((4 + lm) ^ lr) << 4), hv1.x, hv1.y, hv1.z, hv1.w);
        __syncwarp();
        if (lane == 0) {
          mbar_arrive(bars + 8 * BAR_STG);
          mbar_wait(bars + 8 * (BAR_EMPTYB + 4), 1);
          bulk_load(sb + OFF_T + T_TW, tab + T_TW, T_A1 - T_TW, bars + 8 * BAR_T);
          mbar_wait(bars + 8 * BAR_EMPTYB, 0);
#pragma unroll 1
          for (int i = 0; i < 6; i++) tma_load_5d(sb + OFF_Q + i * 4096, &tmQ, bars + 8 * BAR_Q, (chb & ~1) * 8, rank * 32 + i * 4);
        }
        __syncwarp();
      }
      }
      if (MODE != 1) {
        auto korder = [&](int i) { return MODE == 2 ? i : g2_k(hp, i); };
        if (MODE == 0) {
          mbar_wait_idle(bars + 8 * (BAR_EMPTY2 + 2), 0);
          if (elect_one()) {
            mbar_expect_tx(bars + 8 * BAR_FULL2, STG2);
            tma_load_3d(sb + g2_b(0), &tmWo, bars + 8 * BAR_FULL2, 0, korder(0) * 64, cb2 * 2);
            tma_load_3d(sb + g2_b(1), &tmWo, bars + 8 * (BAR_FULL2 + 1), 0, korder(1) * 64, cb2 * 2);
          }
        }
        PROF2(20);
        const __nv_bfloat16* osrc = g_o + (size_t)(rb2 >> 1) * 16 * 16384 + ((rb2 & 1) * 2 + rank) * 4096;
        const uint32_t* flag = g_flag_o + (rb2 >> 1) * 32 + korder(lane & 15) * 2 + (rb2 & 1);
        uint32_t ready = MODE == 0 ? 0u : ~0u, pv = 0;
#pragma unroll
        for (int i = MODE == 0 ? 2 : 0; i < 16; i++) {
          const int kb = korder(i), s = i % NS2, ph = (i / NS2) & 1;
          const uint32_t fb = bars + 8 * (BAR_FULL2 + s);
          if (!((ready >> i) & 1)) {
            int n = 0;
            do {
              ready |= __ballot_sync(0xffffffffu, ld_acquire(flag) == epoch);
            } while (!((ready >> i) & 1) && ++n < SPIN_LIMIT);
            fence_async_all();
          }
          if (i == 2) PROF(21);
          mbar_wait(bars + 8 * (BAR_EMPTY2 + s), ph);
          if (elect_one()) {
            mbar_expect_tx(fb, STG2);
            asm volatile(
                "cp.async.bulk.shared::cluster.global.mbarrier::complete_tx::bytes.multicast::cluster [%0], [%1], %2, [%3], %4;\n"
                ::"r"(sb + g2_a(s) + rank * 8192), "l"(osrc + kb * 16384), "r"(8192), "r"(fb), "h"((uint16_t)3) : "memory");
            if (MODE != 0 || i >= 4) tma_load_3d(sb + g2_b(s), &tmWo, fb, 0, kb * 64, cb2 * 2);
          }
          if (MODE == 0 && i == LA0) pv = ld_relaxed(flag);
          if (MODE == 0 && i == LA1) {
            ready |= __ballot_sync(0xffffffffu, pv == epoch);
            asm volatile("fence.acquire.gpu;\n" ::: "memory");
            fence_async_all();
          }
          if (i == 3) PROF(37);

        }
      }
      __syncwarp();
    } else if (MODE != 2) {
      {
        const int g = lane >> 2, t = lane & 3;
        uint32_t w[2][4];
#pragma unroll
        for (int h = 0; h < 2; h++) {
          const uint2 x = __ldg(reinterpret_cast<const uint2*>(p.shift_k + ((chb & ~1) * 8 + h * 8 + g) * 4));
          w[h][0] = __byte_perm(x.x, x.x, 0x1010);
          w[h][1] = __byte_perm(x.x, x.x, 0x3232);
          w[h][2] = __byte_perm(x.y, x.y, 0x1010);
          w[h][3] = __byte_perm(x.y, x.y, 0x3232);
        }
        auto swz = [](int r) { return (((r & 29) | ((r ^ (r >> 2)) & 2)) << 5) | (r & 16); };
        const uint32_t kring = sb + OFF_H + (hw - 1) * 8192, vring = kring + 4096;
        const int s0 = rank * 32 + (hw - 1) * 11, s1 = hw == 3 ? rank * 32 + 32 : s0 + 11;
        const size_t goff = (size_t)(lane >> 1) * DM + (chb & ~1) * 8 + (lane & 1) * 8;
        const __nv_bfloat16* kg = p.k + goff;
        const __nv_bfloat16* vg = p.v + goff;
        const uint32_t d0 = swz(lane >> 1) ^ ((lane & 1) << 4), d1 = swz(16 + (lane >> 1)) ^ ((lane & 1) << 4);
        auto issue = [&](int st) {
          const uint32_t so = (st & 3) << 10;
          cp_async16(kring + so + d0, kg + (size_t)st * 32 * DM, 16);
          cp_async16(kring + so + d1, kg + (size_t)(st * 32 + 16) * DM, 16);
          cp_async16(vring + so + d0, vg + (size_t)st * 32 * DM, 16);
          cp_async16(vring + so + d1, vg + (size_t)(st * 32 + 16) * DM, 16);
        };
        const int xa = 8 * (lr >> 1) + 2 * lm + (lr & 1), xb = 8 * (lr >> 1) - 4 + 2 * (lm & 1) + (lr & 1);
        const uint32_t la = swz(xa), lb = swz(xb & 31);
        const int backb = xb < 0 ? 1 : 0;
        const uint32_t ud[2] = {mapa(sb + OFF_U + g * 4096 + t * 16, 0), mapa(sb + OFF_U + g * 4096 + t * 16, 1)};
        const uint32_t ub[2] = {mapa(bars + 8 * BAR_U, 0), mapa(bars + 8 * BAR_U, 1)};
        if (lane == 0) mbar_wait(bars + 8 * (BAR_FULLB + NS1B - 1), 0);
        __syncwarp();
        if (lane >= 24) cp_async16(kring + (((s0 - 1) & 3) << 10) + d1, s0 > 0 ? kg + (size_t)(s0 * 32 - 16) * DM : kg, s0 > 0 ? 16 : 0);
        issue(s0);
        asm volatile("cp.async.commit_group;\n" ::: "memory");
        issue(s0 + 1);
        asm volatile("cp.async.commit_group;\n" ::: "memory");
#pragma unroll 1
        for (int st = s0; st < s1; st++) {
          if (st + 2 < s1) issue(st + 2);
          if (hw == 1 && st - s0 < 8) prefetch_l2(p.ssm_k + (size_t)(chb * 8 + st - s0) * SEQ + lane * 64);
          if (hw == 2 && st == s0 + 4 && lane < 2) prefetch_l2(g_tab + (chb * 2 + lane) * 32);
          const uint32_t uo = (st ^ ((g ^ (st >> 2)) & 1)) * 64;
          asm volatile("cp.async.commit_group;\n" ::: "memory");
          asm volatile("cp.async.wait_group 2;\n" ::: "memory");
          __syncwarp();
#pragma unroll
          for (int h = 0; h < 2; h++) {
            uint32_t e[6], vv[4], e4[4];
            ldsm4t(e4, kring + ((st & 3) << 10) + (la ^ (h << 4)));
            ldsm2t(e[0], e[1], kring + (((st - backb) & 3) << 10) + (lb ^ (h << 4)));
            ldsm4t(vv, vring + ((st & 3) << 10) + (la ^ (h << 4)));
            e[2] = e4[0]; e[3] = e4[1]; e[4] = e4[2]; e[5] = e4[3];
            uint32_t o[5];
#pragma unroll
            for (int i = 0; i < 5; i++) o[i] = __byte_perm(e[i], e[i + 1], 0x5432);
#pragma unroll
            for (int i = 0; i < 4; i++) {
              uint32_t a = bmul2(o[i], w[h][3]);
              a = bfma2(e[i + 1], w[h][2], a);
              a = bfma2(o[i + 1], w[h][1], a);
              a = bfma2(e[i + 2], w[h][0], a);
              vv[i] = bmul2(a, vv[i]);
            }
            st_async128(ud[h] + uo, ub[h], vv[0], vv[1], vv[2], vv[3]);
          }
          __syncwarp();
        }
        PROF(16);
      }
      {
        const int rw = (lane >> 3) + (lane & 4), ck = lane & 3;
        const uint32_t so = rw * 64 + ck * 16, dof = rw * 128 + ((ck ^ rw) << 4);
        const uint8_t* hsrc = reinterpret_cast<const uint8_t*>(p.ssm_k + (size_t)chb * 8 * SEQ) + so;
        const float dv = lane < 8 ? __bfloat162float(p.ssm_D[chb * 8 + lane]) : 0.f;
        uint32_t x[32];
        auto load = [&](const uint8_t* src, int i) {
          asm volatile("ld.v4.u32 {%0,%1,%2,%3}, [%4];\n" : "=r"(x[4 * i]), "=r"(x[4 * i + 1]), "=r"(x[4 * i + 2]), "=r"(x[4 * i + 3])
                       : "l"(src + i * 512) : "memory");
        };
#pragma unroll
        for (int i = 0; i < 8; i++) load(hsrc + (hw - 1) * 4096, i);
        nb_sync(NB_HELP3, 96);
        mbar_wait(bars + 8 * BAR_U, 0);
        int eh = 0;
#pragma unroll 1
        for (int n = 2 * (hw - 1); n < 16; n += (n & 1) ? 5 : 1) {
          const int c = n >> 1;
          const uint8_t* nsrc = (n & 1) ? hsrc + (c < 5 ? c + 3 : c) * 4096
                                        : smem + OFF_U + c * 4096 + (so ^ (((c ^ (lane >> 2)) & 1) << 6));
          const uint32_t dst = sb + ((n & 1) ? OFF_U : OFF_H) + c * 4096 + dof;
          const float dc = __shfl_sync(0xffffffffu, dv, c);
          const float h0 = bf_lo(x[0]) + ((lane | (n & 1)) == 0 ? dc : 0.f), h1 = bf_hi(x[0]);
          x[0] = pack_bf16(h0, h1);
          uint32_t m[2] = {x[0], x[1]};
#pragma unroll
          for (int i = 2; i < 32; i++) asm("max.xorsign.abs.bf16x2 %0, %0, %1;\n" : "+r"(m[i & 1]) : "r"(x[i]));
          asm("max.xorsign.abs.bf16x2 %0, %0, %1;\n" : "+r"(m[0]) : "r"(m[1]));
          const uint32_t e = max(__reduce_max_sync(0xffffffffu, max((m[0] >> 7) & 255u, (m[0] >> 23) & 255u)), 5u);
          const uint32_t sc = (259u - e) * 0x00800080u;
#pragma unroll
          for (int i = 0; i < 8; i++) {
            uint32_t o[4];
#pragma unroll
            for (int j = 0; j < 4; j++) {
              const uint32_t v = bmul2(x[4 * i + j], sc);
              asm("cvt.rn.f16x2.f32 %0, %1, %2;\n" : "=r"(o[j]) : "f"(bf_hi(v)), "f"(i + j == 0 ? h0 * bf_hi(sc) : bf_lo(v)));
            }
            sts128((dst + (i & 3) * 1024) ^ ((i >> 2) << 6), o[0], o[1], o[2], o[3]);
            load(nsrc, i);
          }
          if (n & 1) {
            const int f = min(max((int)e + eh - 129, 0), 254);
            if (lane < 2)
              asm volatile("st.async.weak.shared::cluster.mbarrier::complete_tx::bytes.b32 [%0], %2, [%1];\n"
                           ::"r"(mapa(sb + OFF_SC + rank * 32 + c * 4, lane)), "r"(mapa(bars + 8 * BAR_LAND, lane)), "r"(f << 7) : "memory");
          }
          eh = e;
        }
        fence_async_smem();
        __syncwarp();
        if (lane == 0) mbar_arrive(bars + 8 * BAR_UH);
        PROF(32);
      }
      if (hw < 3) {
        const uint32_t rb = mapa(bars, lane & 1);
        const uint32_t epoch = ld_relaxed(g_flag_o + 2 * cta + hw - 1) + 1;
        const bool own = hw - 1 == (rb2 & 1);
        nb_sync(NB_OREADY + hw - 1, 160);
        if (lane == 0) {
          asm volatile("cp.async.bulk.global.shared::cta.bulk_group [%0], [%1], %2;\n" ::"l"(g_o + (size_t)cta * 16384 + (hw - 1) * 8192),
                       "r"(sb + OFF_OP + (own ? 16384 : 0)), "r"(16384) : "memory");
          bulk_commit();
        }
        if (!WAVE && lane < 2) {
          mbar_arrive_cluster(rb + 8 * (BAR_EMPTY2 + 2));
          mbar_arrive_cluster(rb + 8 * (BAR_EMPTY2 + 3));
        }
        if (lane == 0) {
          bulk_wait0();
          if (own) mbar_expect_tx(bars + 8 * (BAR_FULL2 + 1), 16384);
          if (!WAVE || !own) mbar_arrive_cluster(mapa(bars, own ? rank : rank ^ 1) + 8 * BAR_X);
          st_release(g_flag_o + 2 * cta + hw - 1, epoch);
          if (!WAVE || !own) mbar_arrive(bars + 8 * BAR_REL);
        }
        __syncwarp();
        PROF(own ? 17 : 19);
      } else {
        mbar_wait_idle(bars + 8 * BAR_REL, 0);
        if (MODE == 0) {
          mbar_wait(bars + 8 * BAR_X, 0);
          if (elect_one())
            asm volatile("cp.async.bulk.shared::cluster.shared::cta.mbarrier::complete_tx::bytes [%0], [%1], %2, [%3];\n"
                         ::"r"(mapa(sb + OFF_OP, rank ^ 1)), "r"(sb + OFF_OP + 16384), "r"(16384),
                         "r"(mapa(bars + 8 * BAR_FULL2, rank ^ 1)) : "memory");
        }
        if (MODE == 0) {
          mbar_wait_idle(bars + 8 * BAR_DEAD, 0);
          if (elect_one()) {
            tma_load_3d(sb + g2_b(2), &tmWo, bars + 8 * (BAR_FULL2 + 2), 0, g2_k(hp, 2) * 64, cb2 * 2);
            tma_load_3d(sb + g2_b(3), &tmWo, bars + 8 * (BAR_FULL2 + 3), 0, g2_k(hp, 3) * 64, cb2 * 2);
          }
        }
        __syncwarp();
      }
      {
        const int c8 = (4 * (lr >> 1) + 2 * (lm & 1) + (lr & 1)) & 7;
        const bool own = (lr >> 2) == rank;
        const uint32_t ya = sb + (own ? y_slot(c8 & 1, c8 >> 1) : OFF_LAND + c8 * 2048);
        const uint32_t yx = ((lm >> 1) ^ lr) << 4;
        const int row = (lane >> 4) * 8 + ((lane >> 3) & 1) * 16 + ((lane >> 2) & 1);
        uint2* og = reinterpret_cast<uint2*>(p.out + (size_t)(rank * 1024 + row) * (2 * DM) + (chb & ~1) * 8 + (lane & 3) * 4);
        const uint32_t qa = sb + OFF_Q + (lane >> 4) * 512 + (lane & 15) * 8;
        mbar_wait(bars + 8 * BAR_Q, 0);
        mbar_wait_idle(bars + 8 * BAR_LAND, 0);
        PROF(33);
        const uint32_t t0 = clock();
        const uint4 s4 = lds128(sb + OFF_SC + (lane & 3) * 16);
        const uint32_t sc[2] = {s4.x | (s4.y << 16), s4.z | (s4.w << 16)};
        auto fin = [&](uint32_t q2, uint32_t y2, uint32_t s2) {
          float lo, hi;
          asm("{\n.reg .b16 l, h;\nmov.b32 {l, h}, %2;\ncvt.f32.f16 %0, l;\ncvt.f32.f16 %1, h;\n}\n" : "=f"(lo), "=f"(hi) : "r"(y2));
          return bmul2(q2, bmul2(pack_bf16(lo, hi), s2));
        };
#pragma unroll 1
        for (int j = hw - 1; j < 16; j += 3) {
          uint32_t y[4][4];
          uint2 q[8];
          while ((uint32_t)clock() - t0 < j * PACE) __nanosleep(40);
          const uint32_t qj = qa + j * 2048;
#pragma unroll
          for (int i = 0; i < 4; i++) ldsm4t(y[i], ya + j * 128 + (yx ^ (i << 5)));
#pragma unroll
          for (int i = 0; i < 8; i++) q[i] = lds64(qj + (i >> 2) * 1024 + (i & 3) * 128);
#pragma unroll
          for (int i = 0; i < 8; i++) {
            og[(size_t)(j * 64 + (i >> 2) * 32 + (i & 3) * 2) * (2 * DM / 4)] =
                make_uint2(fin(q[i].x, y[i >> 1][2 * (i & 1)], sc[0]), fin(q[i].y, y[i >> 1][2 * (i & 1) + 1], sc[1]));
            if (i < 7) asm volatile("nanosleep.u32 %0;\n" ::"r"(FINE) : "memory");
          }
        }
      }
      PROF(22);
    }
    cluster_sync_all();
  } else {
    asm volatile("setmaxnreg.inc.sync.aligned.u32 %0;\n" :: "n"(REG_MATH));
    if (warp == 0) PROF2(26);
    const int wg = warp >> 2;
    const int wtid = tid & 127;
    const bool signaller = (wtid == 0) || (wtid == 32);
    const uint32_t rbars = mapa(bars, wtid >> 5 & 1);

    if (halo_cta) {
      const uint32_t epoch = ld_relaxed(g_flag_h + blockIdx.x) + 1;
      float acc0[64], acc1[64];
      int s = 0, ph = 0;
#pragma unroll 1
      for (int kb = 0; kb < 16; kb++) {
        mbar_wait(bars + 8 * (BAR_FULLB + s), ph);
        const uint32_t st = sb + s * STGH;
        const uint64_t da = mkdesc(st, 16, 1024, 1);
        const uint64_t db = mkdesc(st + 8192 + wg * 32768, 8192, 1024, 1);
        wg_fence();
#pragma unroll
        for (int kk = 0; kk < 4; kk++) {
          wgmma_n128(acc0, da + 2 * kk, db + 128 * kk, kb + kk);
          wgmma_n128(acc1, da + 2 * kk, db + 1024 + 128 * kk, kb + kk);
        }
        wg_commit();
        wg_wait<0>();
        if (wtid == 0) mbar_arrive(bars + 8 * (BAR_EMPTYB + s));
        if (++s == 3) { s = 0; ph ^= 1; }
      }
      fence_regs(acc0);
      fence_regs(acc1);
      if ((warp & 3) != 3) {
#pragma unroll
        for (int hh = 0; hh < 2; hh++) {
          uint4* dst = g_halo + ((hh * 4 + (warp & 3) + 1) * 16 + blockIdx.x * 4) * 128 + wg * 64 + lane;
#pragma unroll
          for (int j = 0; j < 4; j++) {
            const int o = 16 * j + 2 * hh;
            dst[(j >> 1) * 128 + (j & 1) * 32] =
                make_uint4(pack_bf16(acc0[o], acc0[o + 1]), pack_bf16(acc0[o + 4], acc0[o + 5]),
                           pack_bf16(acc0[o + 8], acc0[o + 9]), pack_bf16(acc0[o + 12], acc0[o + 13]));
            dst[(2 + (j >> 1)) * 128 + (j & 1) * 32] =
                make_uint4(pack_bf16(acc1[o], acc1[o + 1]), pack_bf16(acc1[o + 4], acc1[o + 5]),
                           pack_bf16(acc1[o + 8], acc1[o + 9]), pack_bf16(acc1[o + 12], acc1[o + 13]));
          }
        }
      }
      nb_sync(NB_G1DONE, 256);
      if (tid == 0) st_release(g_flag_h + blockIdx.x, epoch);
      PROF(36);
      cluster_sync_all();
      return;
    }

    float acc[64];
    auto g2_step = [&](int s, int kb) {
      const uint64_t da = mkdesc(sb + g2_a(s) + wg * 8192, 16, 1024, 1);
      const uint64_t db = mkdesc(sb + g2_b(s), 8192, 1024, 1);
      wg_fence();
      wgmma_n128(acc, da, db, kb);
      wgmma_n128(acc, da + 2, db + 128, 1);
      wgmma_n128(acc, da + 4, db + 256, 1);
      wgmma_n128(acc, da + 6, db + 384, 1);
      wg_commit();
    };

    if (MODE != 2) {
    uint32_t a1[2][4], tw[16], d1[32];
    const uint32_t tb = sb + OFF_T + wtid * 16;
    const uint64_t dx = mkdesc(sb + OFF_U + wg * 4096, OFF_H - OFF_U, 1024, 1);
    auto s1 = [&](int it) {
      hmma_n128t<0>(d1, a1[0], dx + it * 512);
      hmma_n128t<1>(d1, a1[1], dx + it * 512 + 128);
      wg_commit();
    };
    auto ldtw = [&](int i) {
      const uint4 v = lds128(tb + T_TW + i * 2048);
      tw[4 * i] = v.x; tw[4 * i + 1] = v.y; tw[4 * i + 2] = v.z; tw[4 * i + 3] = v.w;
    };
    {
      float acc0[96], acc1[96];
      int sa = 0, pha = 0, sbb = 0, phb = 0;
      asm volatile("cp.async.wait_group 0;\n" ::: "memory");
      fence_async_smem();
      nb_sync(NB_FIRST, 256);
      if (tid == 0) {
        mbar_arrive(bars + 8 * BAR_FULLA);
        mbar_arrive(bars + 8 * BAR_FULLB);
      }
      PROF(0 + wg);
#pragma unroll 1
      for (int kb = 0; kb < 30; kb++) {
        if (!(kb & 1)) mbar_wait(bars + 8 * (BAR_FULLA + sa), pha);
        mbar_wait(bars + 8 * (BAR_FULLB + sbb), phb);
        if (kb == 0) PROF2(0 + wg);
        if (kb == 4 && wg == 0) PROF2(28);
        if (kb == 8 && wg == 0) PROF2(29);
        if (kb == 16 && wg == 0) PROF2(30);
        const uint64_t da = mkdesc(sb + sa * STG1A + wg * 16384 + (kb & 1) * 64, 16, 1024, 1);
        const uint64_t db = mkdesc(sb + OFF_1B + sbb * STG1B, 4096, 1024, 1);
        wg_fence();
        wgmma_n192(acc0, da, db, kb);
        wgmma_n192(acc1, da + 512, db, kb);
        wgmma_n192(acc0, da + 2, db + 128, 1);
        wgmma_n192(acc1, da + 514, db + 128, 1);
        wg_commit();
        wg_wait<1>();
        if (kb > 0) {
          if (wtid == 64) mbar_arrive(bars + 8 * (BAR_EMPTYB + (sbb == 0 ? NS1B - 1 : sbb - 1)));
          if (!(kb & 1) && signaller) mbar_arrive_cluster(rbars + 8 * (BAR_EMPTYA + (sa == 0 ? NS1A - 1 : sa - 1)));
        }
        if (++sbb == NS1B) { sbb = 0; phb ^= 1; }
        if ((kb & 1) && ++sa == NS1A) { sa = 0; pha ^= 1; }
      }
      const int blk0 = wg * 8 + (warp & 3);
      const int lr = lane & 7, lm = lane >> 3;
      const bool le0 = 2 * (lane & 3) <= (lane >> 2), le1 = 2 * (lane & 3) + 1 <= (lane >> 2);
      const uint32_t maskLE = (le0 ? 0x0000FFFFu : 0u) | (le1 ? 0xFFFF0000u : 0u);
      uint32_t k0[2][2][4], k1[2][2][4], qa[2][2][8];
      float l[2][2][4];
      {
        static_assert(15 % NS1A == 0 && 30 % NS1B == 0, "slots of the last k blocks");
        mbar_wait(bars + 8 * BAR_FULLA, 1);
        mbar_wait(bars + 8 * BAR_FULLB, 0);
        mbar_wait(bars + 8 * (BAR_FULLB + 1), 0);
        const uint64_t da = mkdesc(sb + wg * 16384, 16, 1024, 1);
        const uint64_t db = mkdesc(sb + OFF_1B, 4096, 1024, 1);
        wg_fence();
#pragma unroll
        for (int i = 0; i < 4; i++) wgmma_n192(acc0, da + 2 * i, db + (i >> 1) * (STG1B >> 4) + (i & 1) * 128, 1);
        wg_commit();
        wg_wait<1>();
        if (wtid == 64) mbar_arrive(bars + 8 * (BAR_EMPTYB + NS1B - 1));
#pragma unroll
        for (int i = 0; i < 2; i++) wgmma_n192(acc1, da + 512 + 2 * i, db + (i >> 1) * (STG1B >> 4) + (i & 1) * 128, 1);
        wg_commit();
        wg_wait<1>();
        fence_regs(acc0);
        attn_stage(sb, blk0, lane, acc0, k1[0]);
#pragma unroll
        for (int i = 2; i < 4; i++) wgmma_n192(acc1, da + 512 + 2 * i, db + (i >> 1) * (STG1B >> 4) + (i & 1) * 128, 1);
        wg_commit();
        attn_pack(acc0, qa[0], k0[0]);
        wg_wait<0>();
        fence_regs(acc1);
      }
      if (wtid == 64) mbar_arrive(bars + 8 * BAR_EMPTYB);
      PROF(2 + wg);
      attn_stage(sb, blk0 + 4, lane, acc1, k1[1]);
      __syncwarp();
      if (lane == 0) mbar_arrive(bars + 8 * BAR_STG);
      mbar_wait(bars + 8 * BAR_U, 0);
      attn_pack(acc1, qa[1], k0[1]);
      attn_own(k0[0], k1[0], le0, le1, qa[0], l[0]);
      attn_own(k0[1], k1[1], le0, le1, qa[1], l[1]);
      const uint32_t cho[2] = {(uint32_t)(((lm & 1) ^ lr) << 4), (uint32_t)(((2 + (lm & 1)) ^ lr) << 4)};
      const uint32_t obase = sb + OFF_OP + (wg == (rb2 & 1) ? 16384 : 0) + ((warp & 3) * 16 + lr) * 128;
      mbar_wait(bars + 8 * BAR_STG, 0);
      {
        uint32_t km[4][4], va[8][4], vb[8][4], pp[8];
        float x[8][2];
#pragma unroll
        for (int n = 0; n < 4; n++) {
          const int blk = blk0 + 4 * (n >> 1);
          to_arr(km[n], lds128(sb + (blk == 0 ? OFF_L0 + 1024 : OFF_KH + (blk - 1) * 2048) + (n & 1) * 512 + lane * 16));
        }
#pragma unroll
        for (int n = 0; n < 8; n++) {
          const int vr = (blk0 + 4 * ((n >> 1) & 1)) * 16 - 8 + 8 * (n >> 2) + 8 * (lm >> 1);
          const uint32_t vrow = sb + (vr < 0 ? OFF_L0 : OFF_VP + vr * 128) + lr * 128;
          ldsm4t(va[n], vrow + (cho[0] ^ ((n & 1) << 6)));
          ldsm4t(vb[n], vrow + (cho[1] ^ ((n & 1) << 6)));
        }
        const bool first = blk0 == 0 && gidx == 0;
#pragma unroll
        for (int n = 0; n < 4; n++) {
          const uint32_t(&q)[8] = qa[n >> 1][n & 1];
          float sm[4];
          mma16816_z(sm, q[0], q[1], q[2], q[3], km[n][0], km[n][1]);
          mma16816(sm, q[4], q[5], q[6], q[7], km[n][2], km[n][3]);
          if (n < 2 && first) sm[0] = sm[1] = -1e9f / 0.17677669529663687f;
          x[n][0] = le0 ? l[n >> 1][n & 1][0] : sm[0];
          x[n][1] = le1 ? l[n >> 1][n & 1][1] : sm[1];
          x[4 + n][0] = l[n >> 1][n & 1][2];
          x[4 + n][1] = l[n >> 1][n & 1][3];
        }
        quad_softmax<8>(x, pp);
#pragma unroll
        for (int n = 7; n >= 0; n--)
          attn_pv(obase + ((n >> 1) & 1) * 8192 + (n >> 2) * 1024 + (((4 * (n & 1) + lm) ^ lr) << 4), va[n], vb[n], pp[n],
                  maskLE);
      }
      fence_async_smem();
      nb_arrive(NB_OREADY + wg, 160);
    }

    {
      const int w = warp & 3;
      uint32_t a4[8][4];
      uint32_t d4[8];
      PROF(34 + wg);
      const uint64_t dz = mkdesc(sb + OFF_U + wg * 4096, 512, 128, 0);
      const uint64_t db2 = mkdesc(sb + OFF_T + T_B2, 128, 256, 0);
      mbar_wait(bars + 8 * BAR_T, 0);
      mbar_wait(bars + 8 * BAR_UH, 0);
      to_arr(a1[0], lds128(tb + T_A1));
      to_arr(a1[1], lds128(tb + T_A1 + 2048));
      wg_fence();
      s1(0);
      ldtw(0);
      ldtw(1);
      const uint32_t za = sb + (w < 2 ? OFF_U : OFF_H) + wg * 4096 + (w & 1) * 2048 + lane * 16;
      const uint32_t yl = (wtid ^ (4 * rank + wg)) * 16;
      const uint32_t yown = mapa(sb, rank) + yl, yrem = mapa(sb + OFF_LAND + wg * 2048, rank ^ 1) + yl;
      const uint32_t yb[2] = {mapa(bars + 8 * BAR_LAND, 0), mapa(bars + 8 * BAR_LAND, 1)};
      wg_wait<0>();
      fence_regs(d1);
      nb_sync(NB_WG + wg, 128);
      auto s4 = [&](int it) {
        wg_fence();
#pragma unroll
        for (int ks = 0; ks < 8; ks++) {
          const uint64_t d = dz + (it & 1) * 512 + (ks & 3) * 64 + (ks >> 2) * ((OFF_H - OFF_U) >> 4);
          if (ks == 0) hmma_n32<0, 1>(d4, a4[ks], d);
          else hmma_n32<1, 1>(d4, a4[ks], d);
        }
        wg_commit();
      };
      auto e4 = [&](int it) {
        fence_regs(d4);
        const uint32_t o = (yown + y_slot(wg, it)) ^ ((it >> 1) << 5), m = (yrem + it * 4096) ^ ((it >> 1) << 5);
        if (it == 0) mbar_wait(bars + 8 * BAR_LFREE, 0);
        if (it == 3) mbar_wait(bars + 8 * (BAR_DEAD + 1), 0);
        st_async128(rank ? m : o, yb[0], d4[0], d4[1], d4[2], d4[3]);
        st_async128(rank ? o : m, yb[1], d4[4], d4[5], d4[6], d4[7]);
      };
      uint32_t a2[2][2][2][4], a3[2][2][4], d2[2][2][8], d3[2][8];
      auto s2a = [&]() {
        wg_fence();
#pragma unroll
        for (int c = 0; c < 4; c++) hmma_n32<0, 0>(d2[c & 1][c >> 1], a2[0][c & 1][c >> 1], db2 + (c >> 1) * 128);
      };
      auto s2b = [&]() {
        wg_fence();
#pragma unroll
        for (int c = 0; c < 4; c++) {
          hmma_n32<1, 0>(d2[c & 1][c >> 1], a2[1][c & 1][c >> 1], db2 + (c >> 1) * 128 + 64);
          if (c & 1) wg_commit();
        }
      };
      auto done = [&](int it) {
        if (it == 0) {
          if (signaller) mbar_arrive_cluster(rbars + 8 * BAR_LFREE);
        } else if (it >= 2 && wtid == 64) {
          mbar_arrive(bars + 8 * (BAR_DEAD + it - 2));
        }
        if (w == 0) PROF3(40 + 4 * wg + it);
      };
      fft_e1<0>(d1, tw, a2[0]);
      s2a();
      fft_e1<1>(d1, tw, a2[1]);
      s2b();
      s1(1);
      ldtw(2);
      ldtw(3);
#pragma unroll
      for (int i = 0; i < 8; i++) to_arr(a4[i], lds128(tb + T_A4 + i * 2048));
#pragma unroll
      for (int it = 0; it < 4; it++) {
        if (it == 0 || it == 3) wg_wait<2>(); else wg_wait<3>();
        fence_regs(d2[0][0]);
        fence_regs(d2[1][0]);
        fft_e2<0, 0>(d2[0][0], d2[1][0], a3[0]);
        fft_e2<0, 1>(d2[0][0], d2[1][0], a3[1]);
        if (it == 0 || it == 3) wg_wait<1>(); else wg_wait<2>();
        fence_regs(d2[0][1]);
        fence_regs(d2[1][1]);
        fft_e2<1, 0>(d2[0][1], d2[1][1], a3[0]);
        fft_e2<1, 1>(d2[0][1], d2[1][1], a3[1]);
        wg_fence();
        hmma_n32<0, 0>(d3[0], a3[0][0], db2);
        hmma_n32<0, 0>(d3[1], a3[0][1], db2);
        hmma_n32<1, 0>(d3[0], a3[1][0], db2 + 64);
        hmma_n32<1, 0>(d3[1], a3[1][1], db2 + 64);
        wg_commit();
        wg_wait<1>();
        if (it > 0) e4(it - 1);
        if (it < 3) {
          fence_regs(d1);
          fft_e1<0>(d1, tw, a2[0]);
        }
        wg_wait<0>();
        fence_regs(d3[0]);
        fence_regs(d3[1]);
        if (it < 3) s2a();
        fft_e3(d3, tw, za + (it & 1) * 8192);
        if (it < 3) {
          fft_e1<1>(d1, tw, a2[1]);
          s2b();
        }
        fence_async_smem();
        nb_sync(NB_WG + wg, 128);
        done(it);
        s4(it);
        if (it < 2) s1(it + 2);
      }
      if (PEEL && MODE == 0) {
        mbar_wait(bars + 8 * BAR_FULL2, 0);
        g2_step(0, 0);
        wg_wait<1>();
      } else {
        wg_wait<0>();
      }
      if (signaller) mbar_arrive_cluster(rbars + 8 * (BAR_EMPTY2 + 4));
      e4(3);
      if (PEEL && MODE == 0) {
        wg_wait<0>();
        if (signaller) mbar_arrive_cluster(rbars + 8 * BAR_EMPTY2);
      }
      PROF(6 + wg);
    }
    }

    if (MODE != 1) {
      int s = PEEL && MODE == 0, ph = 0;
#pragma unroll 1
      for (int kb = s; kb < STAG; kb++) {
        mbar_wait(bars + 8 * (BAR_FULL2 + s), ph);
        if (kb == 1) PROF(8 + wg);
        if (warp == 4) PROF2(40 + kb);
        g2_step(s, kb);
        wg_wait<0>();
        if (kb < 16 - NS2 && signaller) mbar_arrive_cluster(rbars + 8 * (BAR_EMPTY2 + s));
        if (++s == NS2) { s = 0; ph ^= 1; }
      }
      if (STAG < 16) {
        if (wg == LAST) nb_sync(NB_LEAD, 256);
#pragma unroll
        for (int kb = STAG; kb < 16; kb++) {
          mbar_wait(bars + 8 * (BAR_FULL2 + kb % NS2), (kb / NS2) & 1);
          g2_step(kb % NS2, 1);
        }
        if (wg != LAST) nb_arrive(NB_LEAD, 256);
      }
      wg_wait<0>();
      fence_regs(acc);
      PROF(10 + wg);
      const int lr = lane & 7, lm = lane >> 3;
      const uint32_t wbase = sb + warp * 2048;
      const uint32_t base = wbase + (lr + 8 * (lm & 1)) * 128;
#pragma unroll
      for (int j = 0; j < 16; j += 2) {
        const uint32_t a = base + (j >> 3) * 16384 + ((((j & 7) + (lm >> 1)) ^ lr) << 4);
        stsm4(a, pack_bf16(acc[4 * j], acc[4 * j + 1]), pack_bf16(acc[4 * j + 2], acc[4 * j + 3]),
              pack_bf16(acc[4 * j + 4], acc[4 * j + 5]), pack_bf16(acc[4 * j + 6], acc[4 * j + 7]));
      }
      __syncwarp();
      {
        const int rr = lane >> 4, ck = lane & 7, hf = (lane >> 3) & 1;
        uint4* og = reinterpret_cast<uint4*>(p.out + (size_t)(2 * ((rb2 & 7) * 128 + warp * 16 + rr) + (rb2 >> 3)) * (2 * DM) + DM + cb2 * 128 + hf * 64 + ck * 8);
        uint4 v[8];
#pragma unroll
        for (int i = 0; i < 8; i++) v[i] = lds128(wbase + hf * 16384 + (2 * i + rr) * 128 + ((ck ^ ((2 * i + rr) & 7)) << 4));
#pragma unroll
        for (int i = 0; i < 8; i++) og[(size_t)i * 4 * (2 * DM / 8)] = v[i];
      }
      PROF(12 + wg);
    }
    cluster_sync_all();
  }
}

typedef CUresult (*EncodeFn)(CUtensorMap*, CUtensorMapDataType, cuuint32_t, void*, const cuuint64_t*, const cuuint64_t*,
                             const cuuint32_t*, const cuuint32_t*, CUtensorMapInterleave, CUtensorMapSwizzle,
                             CUtensorMapL2promotion, CUtensorMapFloatOOBfill);

void make_map(EncodeFn enc, CUtensorMap* tm, const void* base, int rank, const cuuint64_t* dims, const cuuint64_t* strides,
              const cuuint32_t* box, CUtensorMapSwizzle swz) {
  cuuint32_t es[5] = {1, 1, 1, 1, 1};
  enc(tm, CU_TENSOR_MAP_DATA_TYPE_BFLOAT16, rank, const_cast<void*>(base), dims, strides, box, es,
      CU_TENSOR_MAP_INTERLEAVE_NONE, swz, CU_TENSOR_MAP_L2_PROMOTION_L2_256B, CU_TENSOR_MAP_FLOAT_OOB_FILL_NONE);
}

}

extern "C" void kernel_launch(void* const* d_in, const int* in_sizes, int n_in, void* d_out, int out_size) {
  static EncodeFn enc = nullptr;
  static bool coresident = true;
  if (!enc) {
    void* fn = nullptr;
    cudaDriverEntryPointQueryResult qr;
    cudaGetDriverEntryPoint("cuTensorMapEncodeTiled", &fn, cudaEnableDefault, &qr);
    enc = (EncodeFn)fn;
    cudaFuncSetAttribute(fused_kernel<0>, cudaFuncAttributeMaxDynamicSharedMemorySize, SMEM_BYTES);
    cudaFuncSetAttribute(fused_kernel<1>, cudaFuncAttributeMaxDynamicSharedMemorySize, SMEM_BYTES);
    cudaFuncSetAttribute(fused_kernel<2>, cudaFuncAttributeMaxDynamicSharedMemorySize, SMEM_BYTES);
    cudaLaunchConfig_t cfg = {};
    cfg.gridDim = dim3(NCTA);
    cfg.blockDim = dim3(NTHREADS);
    cfg.dynamicSmemBytes = SMEM_BYTES;
    cudaLaunchAttribute at;
    at.id = cudaLaunchAttributeClusterDimension;
    at.val.clusterDim.x = 2;
    at.val.clusterDim.y = 1;
    at.val.clusterDim.z = 1;
    cfg.attrs = &at;
    cfg.numAttrs = 1;
    int nclusters = 0;
    if (cudaOccupancyMaxActiveClusters(&nclusters, fused_kernel<0>, &cfg) == cudaSuccess) coresident = nclusters >= NCTA / 2;
    (void)cudaGetLastError();
  }
  CUtensorMap tmX, tmW, tmWo, tmQ, tmXh, tmWh;
  {
    cuuint64_t dims[3] = {1024, 2, 1024};
    cuuint64_t str[2] = {2048, 4096};
    cuuint32_t box[3] = {64, 1, 128};
    make_map(enc, &tmX, d_in[6], 3, dims, str, box, CU_TENSOR_MAP_SWIZZLE_128B);
  }
  {
    cuuint64_t dims[3] = {1024, 1024, 3};
    cuuint64_t str[2] = {6144, 2048};
    cuuint32_t box[3] = {64, 32, 3};
    make_map(enc, &tmW, d_in[7], 3, dims, str, box, CU_TENSOR_MAP_SWIZZLE_128B);
  }
  {
    cuuint64_t dims[3] = {64, 1024, 16};
    cuuint64_t str[2] = {2048, 128};
    cuuint32_t box[3] = {64, 64, 2};
    make_map(enc, &tmWo, d_in[8], 3, dims, str, box, CU_TENSOR_MAP_SWIZZLE_128B);
  }
  {
    cuuint64_t dims[5] = {1024, 2, 2, 8, 64};
    cuuint64_t str[4] = {2048, 16 * 2048, 2 * 2048, 32 * 2048};
    cuuint32_t box[5] = {16, 2, 2, 8, 4};
    make_map(enc, &tmQ, d_in[0], 5, dims, str, box, CU_TENSOR_MAP_SWIZZLE_NONE);
  }
  {
    cuuint64_t dims[4] = {1024, 256, 2, 4};
    cuuint64_t str[3] = {4096, 2048, 256 * 4096};
    cuuint32_t box[4] = {64, 8, 2, 4};
    make_map(enc, &tmXh, d_in[6], 4, dims, str, box, CU_TENSOR_MAP_SWIZZLE_128B);
  }
  {
    cuuint64_t dims[3] = {64, 1024, 48};
    cuuint64_t str[2] = {6144, 128};
    cuuint32_t box[3] = {64, 64, 4};
    make_map(enc, &tmWh, d_in[7], 3, dims, str, box, CU_TENSOR_MAP_SWIZZLE_128B);
  }
  Params p;
  p.q = (const __nv_bfloat16*)d_in[0];
  p.k = (const __nv_bfloat16*)d_in[1];
  p.v = (const __nv_bfloat16*)d_in[2];
  p.shift_k = (const __nv_bfloat16*)d_in[3];
  p.ssm_k = (const __nv_bfloat16*)d_in[4];
  p.ssm_D = (const __nv_bfloat16*)d_in[5];
  p.x = (const __nv_bfloat16*)d_in[6];
  p.w = (const __nv_bfloat16*)d_in[7];
  p.wo = (const __nv_bfloat16*)d_in[8];
  p.out = (__nv_bfloat16*)d_out;
  if (coresident) {
    fused_kernel<0><<<NCTA, NTHREADS, SMEM_BYTES>>>(p, tmX, tmW, tmWo, tmQ, tmXh, tmWh);
  } else {
    fused_kernel<0><<<4, NTHREADS, SMEM_BYTES>>>(p, tmX, tmW, tmWo, tmQ, tmXh, tmWh);
    fused_kernel<1><<<NCTA, NTHREADS, SMEM_BYTES>>>(p, tmX, tmW, tmWo, tmQ, tmXh, tmWh);
    fused_kernel<2><<<NCTA, NTHREADS, SMEM_BYTES>>>(p, tmX, tmW, tmWo, tmQ, tmXh, tmWh);
  }
}
```

```cpp
#include <cuda_runtime.h>
#include <cuda.h>
#include <cuda_bf16.h>
#include <stdint.h>

namespace {

constexpr int SEQ = 2048;
constexpr int DM = 1024;
constexpr int NCTA = 132;
constexpr int NTHREADS = 384;

constexpr int STG1A = 32768;
constexpr int NS1A = 3;
constexpr int STG1B = 12288;
constexpr int NS1B = 5;
constexpr int OFF_1B = NS1A * STG1A;
constexpr int STG2 = 32768;
constexpr int NS2 = 5;
constexpr int STGH = 73728;
constexpr int OFF_VP = 0;
constexpr int OFF_KH = 1 * STG2;
constexpr int OFF_OP = 2 * STG2;
constexpr int OFF_Q = 3 * STG2;
constexpr int T_A4 = 0, T_TW = 16384, T_B2 = 24576, T_A1 = 28672, T_END = 32768;
constexpr int OFF_U = 163840;
constexpr int OFF_H = OFF_U + 32768;
constexpr int OFF_T = OFF_U - T_END;
constexpr int OFF_LAND = 4 * STG2;
constexpr int OFF_BAR = OFF_H + 32768;
constexpr int OFF_SC = OFF_BAR + 512;
constexpr int OFF_L0 = OFF_BAR + 1024;
constexpr int SMEM_BYTES = OFF_L0 + 2048;
static_assert(OFF_T + T_A1 == OFF_1B + NS1B * STG1B && OFF_T + T_TW == OFF_1B + 4 * STG1B && OFF_LAND == OFF_T + T_A4, "layout");
static_assert(3 * STGH <= OFF_BAR && SMEM_BYTES <= 232448, "smem");

constexpr int BAR_FULLA = 0;
constexpr int BAR_EMPTYA = 3;
constexpr int BAR_FULLB = 6;
constexpr int BAR_EMPTYB = 11;
constexpr int BAR_FULL2 = 16;
constexpr int BAR_EMPTY2 = 21;
constexpr int BAR_T = 26;
constexpr int BAR_UH = 27;
constexpr int BAR_LFREE = 28;
constexpr int BAR_LAND = 29;
constexpr int BAR_U = 30;
constexpr int BAR_Q = 31;
constexpr int BAR_STG = 32;
constexpr int BAR_DEAD = 33;
constexpr int BAR_X = 35;
constexpr int BAR_REL = 36;

constexpr int NB_G1DONE = 1;
constexpr int NB_OREADY = 2;
constexpr int NB_WG = 4;
constexpr int NB_HELP3 = 6;
constexpr int NB_FIRST = 7;
constexpr int NB_LEAD = 8;

#define PACE 390u
#define PF0 20
#define EARLYS1 0
#define PEEL 1
#define IDLEW 1
#define LA0 3
#define LA1 4
#define STAG 12
#define LAST 0
#define FINE 40
#define POLL1 0
#define SCHED 1
#define REG_MATH 224
#define REG_HELP 56
constexpr int SPIN_LIMIT = 1 << 20;

__device__ __align__(1024) __nv_bfloat16 g_o[SEQ * DM];
__device__ uint32_t g_flag_o[256];
__device__ uint32_t g_flag_h[4];
__device__ uint4 g_halo[128 * 128];
__device__ __align__(128) const uint32_t g_tab[T_END / 4] = {
0x3c003c00,0x3bf13bff,0,0xafd6a648,0x3c003c00,0x3b993bce,0,0xb505b303,0x3c003c00,0x3af63b50,0,0xb7e3b67c,
0x3c003c00,0x3a0f3a8a,0,0xb93ab89b,0x3bc33bfe,0x3b773bfa,0xb3c6aa48,0xb5c2acb5,0x3a6d3b3b,0x389b3a4f,0xb8c4b6d7,0xba8ab8ec,
0x381d395f,0x26483505,0xbaddb9ed,0xbbffbb99,0x30b23564,0xb848b444,0xbbeabb88,0xbac2bbb6,0x3b0e3bf6,0x3a8a3bf1,0xb78bae46,0xb89bafd6,
0x34a53913,0xa6483732,0xbba8ba2f,0xbbffbb25,0xb78bae46,0xbac2b7e3,0xbb0ebbf6,0xb848baf6,0xbba8ba2f,0xbb50bbfa,0xb4a5b913,0x367cacb5,
0x39ed3bea,0x393a3be2,0xb95fb0b2,0xba0fb179,0xb56433c6,0xb8ec2648,0xbb88bbc3,0xba4fbbff,0xbbfeba6d,0xbb25bbce,0xaa48b8c4,0x3732b303,
0xb6d7badd,0x3444b67c,0x3b3b381d,0x3bb63b50,0x38723bd9,0x37323bce,0xbaa7b23e,0xbb25b303,0xbaa7b23e,0xbbb6b67c,0xb872bbd9,0xb444bb50,
0xb872bbd9,0xacb5ba8a,0x3aa7323e,0x3bfa389b,0x3aa7323e,0x3bf139cb,0x38723bd9,0xafd63984,0x35643bc3,0x33033bb6,0xbb88b3c6,0xbbceb444,
0xbbfeb8c4,0xbb77ba0f,0x2a48ba6d,0x35c2b93a,0x36d7b81d,0x3a8aafd6,0x3b3b3add,0x389b3bf1,0x395f3bea,0x26483b25,0xb9ed30b2,0xbbffb732,
0x2e463ba8,0xa6483b99,0xbbf6b4a5,0xbbffb505,0xba2fbb0e,0xb848bbb6,0x3913b78b,0x3ac2b444,0x3bf634a5,0x3b50393a,0x2e463ba8,0xb67c3a0f,
0xb913378b,0xbbe2afd6,0xba2fbb0e,0xb179bbf1,0xb0b23b88,0xb4443b77,0xbbeab564,0xbbb6b5c2,0xb3c6bbfe,0x2cb5bbe2,0x3bc3aa48,0x3bfa3179,
0x38c43b3b,0x2fd63bff,0xba6d36d7,0xbbf12648,0xbaddb95f,0xb505bbce,0x381db9ed,0x3b99b303,0xb61f3b64,0xb7e33b50,0xbb64b61f,0xbaf6b67c,
0x361fbb64,0x393aba8a,0x3b64361f,0x3a0f389b,0xb61f3b64,0xba4f3984,0xbb64b61f,0xb8ecb9cb,0x361fbb64,0x3b25b848,0x3b64361f,0x37323ac2,
0xb8c43b3b,0xb9843b25,0xba6db6d7,0xb9cbb732,0x3addb95f,0x3bceb7e3,0x381d39ed,0x33033af6,0xbbea3564,0xbb77acb5,0xb0b2bb88,0x35c2bbfa,
0x3bc32a48,0x389b38ec,0xb3c63bfe,0xba8a3a4f,0xba2f3b0e,0xbac23af6,0xb913b78b,0xb848b7e3,0x3bf6b4a5,0x3b50acb5,0xae463ba8,0xb67c3bfa,
0xb913b78b,0xb179ba4f,0x3a2fbb0e,0x3be2b8ec,0xae463ba8,0xb9cb3b99,0xbbf634a5,0xb984b505,0xbb3b3add,0xbb993ac2,0xb6d7b81d,0xb505b848,
0x39ed30b2,0x37e335c2,0xb95f3bea,0xbaf63b77,0x3564bbc3,0x3a0fbbe2,0x3b88b3c6,0x393a3179,0xbbfe38c4,0xba4f2648,0xaa48ba6d,0x38ecbbff,
0xbbd93aa7,0xbbfa3a8a,0xb23eb872,0xacb5b89b,0x323e3872,0xafd639cb,0xbbd93aa7,0xbbf13984,0x3bd9baa7,0x3b99b848,0x323e3872,0xb5053ac2,
0xb23eb872,0x37e3bb77,0x3bd9baa7,0x3af6b5c2,0xbbfe3a6d,0xbbe23a4f,0x2a48b8c4,0x3179b8ec,0xb6d73add,0xb9843b99,0xbb3b381d,0xb9cb3505,
0x395fb0b2,0x33033444,0xb9ed3bea,0xbbce3bb6,0x3b88bbc3,0x3b77b93a,0x356433c6,0xb5c23a0f,0xbba83a2f,0xbb503a0f,0x34a5b913,0x367cb93a,
0xbb0e3bf6,0xbbe23bf1,0xb78b2e46,0xb179afd6,0xb4a53913,0xb9cb3b25,0xbba83a2f,0xb9843732,0x378bae46,0xb30337e3,0xbb0e3bf6,0xbbce3af6,
0xbadd39ed,0xba4f39cb,0x381db95f,0x38ecb984,0xbbea3b88,0xbb253ac2,0x30b2b564,0x3732b848,0xbbc33bfe,0xbbb63b77,0xb3c62a48,0x3444b5c2,
0xba6d3b3b,0xbbfa3be2,0xb8c436d7,0x2cb5b179,0xb9a839a8,0xb8ec3984,0x39a8b9a8,0x3a4fb9cb,0xb9a839a8,0xb7323848,0x39a8b9a8,0x3b25bac2,
0xb9a839a8,0xb44435c2,0x39a8b9a8,0x3bb6bb77,0xb9a839a8,0xacb53179,0x39a8b9a8,0x3bfabbe2,0xb81d395f,0xb67c393a,0x3addb9ed,0x3b50ba0f,
0xb0b23564,0x31792fd6,0x3beabb88,0x3be2bbf1,0x33c6aa48,0x3984b732,0x3bc3bbfe,0x39cbbb25,0x38c4b6d7,0x3bcebaf6,0x3a6dbb3b,0x3303b7e3,
0xb4a53913,0xb17938ec,0x3ba8ba2f,0x3be2ba4f,0x378bae46,0x39cbb505,0x3b0ebbf6,0x3984bb99,0x3ba8ba2f,0x3bcebbb6,0x34a5b913,0xb303b444,
0x3b0ebbf6,0x35c2ba0f,0xb78b2e46,0xbb77393a,0xaa4838c4,0x2cb5389b,0x3bfeba6d,0x3bfaba8a,0x3b3bb81d,0x3bf1b984,0x36d7badd,0x2fd6b9cb,
0x39edbbea,0x3505bac2,0xb95f30b2,0xbb993848,0xb564b3c6,0xbaf635c2,0xbb883bc3,0xb7e33b77,0x323e3872,0x35053848,0x3bd9baa7,0x3b99bac2,
0x3bd9baa7,0x3af6bb77,0xb23eb872,0xb7e3b5c2,0xb23eb872,0xb93ab179,0xbbd93aa7,0xba0f3be2,0xbbd93aa7,0xb8ec3bff,0x323e3872,0x3a4fa648,
0x36d7381d,0x384837e3,0x3b3bbadd,0x3ac2baf6,0x395fbbea,0x367cbbfa,0xb9edb0b2,0xbb502cb5,0xbb8833c6,0xbbe238ec,0xb5643bc3,0x31793a4f,
0x2a483a6d,0x39843505,0x3bfeb8c4,0x39cbbb99,0x3913378b,0x39cb3732,0x3a2fbb0e,0x3984bb25,0x2e46bba8,0xb303baf6,0xbbf634a5,0xbbce37e3,
0xba2f3b0e,0xb5c23bfa,0x3913378b,0x3b772cb5,0x3bf6b4a5,0x3a8aba4f,0x2e46bba8,0xb89bb8ec,0x3a6d36d7,0x3af6367c,0x38c4bb3b,0x37e3bb50,
0xb81db9ed,0xba0fb89b,0xbadd395f,0xb93a3a8a,0x30b23b88,0x38ec39cb,0x3beab564,0x3a4fb984,0x33c6bbfe,0xb732bac2,0xbbc3aa48,0xbb253848,
0x3b64361f,0x3bb635c2,0x361fbb64,0x3444bb77,0xbb64b61f,0xbbfab179,0xb61f3b64,0xacb53be2,0x3b64361f,0x3bf1a648,0x361fbb64,0xafd6bbff,
0xbb64b61f,0xbb993303,0xb61f3b64,0x35053bce,0x3bea3564,0x3bff3505,0x30b2bb88,0x2648bb99,0xbbc32a48,0xbac23444,0x33c63bfe,0x38483bb6,
0x3a6db6d7,0x367cba0f,0xb8c4bb3b,0xbb50b93a,0xb81d39ed,0x31793bf1,0x3add395f,0x3be22fd6,0x3bf634a5,0x3bce3444,0xae46bba8,0xb303bbb6,
0xb913378b,0xb5c2393a,0x3a2f3b0e,0x3b773a0f,0xae46bba8,0xb89bbbf1,0xbbf6b4a5,0xba8a2fd6,0x3a2f3b0e,0x3bff3732,0x3913b78b,0xa648bb25,
0x3b8833c6,0x3b253303,0xb564bbc3,0xb732bbce,0xaa483a6d,0x34443b50,0x3bfe38c4,0x3bb6367c,0xbb3bbadd,0xbbfab89b,0xb6d7381d,0x2cb53a8a,
0x39edb0b2,0x2fd6b984,0xb95fbbea,0xbbf1b9cb,0x3aa7323e,0x3a0f3179,0xb872bbd9,0xb93abbe2,0x38723bd9,0x3a4f3bff,0x3aa7323e,0x38eca648,
0xbaa7b23e,0xb7323303,0x38723bd9,0x3b253bce,0xb872bbd9,0xbbb6bb50,0xbaa7b23e,0xb444367c,0x395f30b2,0x389b2fd6,0xb9edbbea,0xba8abbf1,
0x3b883bc3,0x3bff3b25,0x3564b3c6,0x2648b732,0x2a4838c4,0x38483af6,0x3bfe3a6d,0x3ac237e3,0xbb3bb81d,0xb67c2cb5,0x36d73add,0x3b503bfa,
0x378b2e46,0x35c22cb5,0xbb0ebbf6,0xbb77bbfa,0x3ba83a2f,0x3a8a38ec,0xb4a5b913,0xb89bba4f,0x3b0e3bf6,0x3bff3b99,0x378b2e46,0xa648b505,
0x34a53913,0x3ac23bb6,0x3ba83a2f,0x38483444,0x33c62a48,0x2fd62648,0xbbc3bbfe,0xbbf1bbff,0x38c436d7,0x35053303,0xba6dbb3b,0xbb99bbce,
0x3add39ed,0x37e3367c,0xb81db95f,0xbaf6bb50,0x3bea3b88,0x393a389b,0xb0b2b564,0xba0fba8a,0x3c003c00,0xbbf1bbff,0,0x2fd62648,
0x3c003c00,0xbb99bbce,0,0x35053303,0x3c003c00,0xbaf6bb50,0,0x37e3367c,0x3c003c00,0xba0fba8a,0,0x393a389b,
0x3bc33bfe,0xbb77bbfa,0xb3c6aa48,0x35c22cb5,0x3a6d3b3b,0xb89bba4f,0xb8c4b6d7,0x3a8a38ec,0x381d395f,0xa648b505,0xbaddb9ed,0x3bff3b99,
0x30b23564,0x38483444,0xbbeabb88,0x3ac23bb6,0x3b0e3bf6,0xba8abbf1,0xb78bae46,0x389b2fd6,0x34a53913,0x2648b732,0xbba8ba2f,0x3bff3b25,
0xb78bae46,0x3ac237e3,0xbb0ebbf6,0x38483af6,0xbba8ba2f,0x3b503bfa,0xb4a5b913,0xb67c2cb5,0x39ed3bea,0xb93abbe2,0xb95fb0b2,0x3a0f3179,
0xb56433c6,0x38eca648,0xbb88bbc3,0x3a4f3bff,0xbbfeba6d,0x3b253bce,0xaa48b8c4,0xb7323303,0xb6d7badd,0xb444367c,0x3b3b381d,0xbbb6bb50,
0x38723bd9,0xb732bbce,0xbaa7b23e,0x3b253303,0xbaa7b23e,0x3bb6367c,0xb872bbd9,0x34443b50,0xb872bbd9,0x2cb53a8a,0x3aa7323e,0xbbfab89b,
0x3aa7323e,0xbbf1b9cb,0x38723bd9,0x2fd6b984,0x35643bc3,0xb303bbb6,0xbb88b3c6,0x3bce3444,0xbbfeb8c4,0x3b773a0f,0x2a48ba6d,0xb5c2393a,
0x36d7b81d,0xba8a2fd6,0x3b3b3add,0xb89bbbf1,0x395f3bea,0xa648bb25,0xb9ed30b2,0x3bff3732,0x2e463ba8,0x2648bb99,0xbbf6b4a5,0x3bff3505,
0xba2fbb0e,0x38483bb6,0x3913b78b,0xbac23444,0x3bf634a5,0xbb50b93a,0x2e463ba8,0x367cba0f,0xb913378b,0x3be22fd6,0xba2fbb0e,0x31793bf1,
0xb0b23b88,0x3444bb77,0xbbeab564,0x3bb635c2,0xb3c6bbfe,0xacb53be2,0x3bc3aa48,0xbbfab179,0x38c43b3b,0xafd6bbff,0xba6d36d7,0x3bf1a648,
0xbaddb95f,0x35053bce,0x381db9ed,0xbb993303,0xb61f3b64,0x37e3bb50,0xbb64b61f,0x3af6367c,0x361fbb64,0xb93a3a8a,0x3b64361f,0xba0fb89b,
0xb61f3b64,0x3a4fb984,0xbb64b61f,0x38ec39cb,0x361fbb64,0xbb253848,0x3b64361f,0xb732bac2,0xb8c43b3b,0x3984bb25,0xba6db6d7,0x39cb3732,
0x3addb95f,0xbbce37e3,0x381d39ed,0xb303baf6,0xbbea3564,0x3b772cb5,0xb0b2bb88,0xb5c23bfa,0x3bc32a48,0xb89bb8ec,0xb3c63bfe,0x3a8aba4f,
0xba2f3b0e,0x3ac2baf6,0xb913b78b,0x384837e3,0x3bf6b4a5,0xbb502cb5,0xae463ba8,0x367cbbfa,0xb913b78b,0x31793a4f,0x3a2fbb0e,0xbbe238ec,
0xae463ba8,0x39cbbb99,0xbbf634a5,0x39843505,0xbb3b3add,0x3b99bac2,0xb6d7b81d,0x35053848,0x39ed30b2,0xb7e3b5c2,0xb95f3bea,0x3af6bb77,
0x3564bbc3,0xba0f3be2,0x3b88b3c6,0xb93ab179,0xbbfe38c4,0x3a4fa648,0xaa48ba6d,0xb8ec3bff,0xbbd93aa7,0x3bfaba8a,0xb23eb872,0x2cb5389b,
0x323e3872,0x2fd6b9cb,0xbbd93aa7,0x3bf1b984,0x3bd9baa7,0xbb993848,0x323e3872,0x3505bac2,0xb23eb872,0xb7e33b77,0x3bd9baa7,0xbaf635c2,
0xbbfe3a6d,0x3be2ba4f,0x2a48b8c4,0xb17938ec,0xb6d73add,0x3984bb99,0xbb3b381d,0x39cbb505,0x395fb0b2,0xb303b444,0xb9ed3bea,0x3bcebbb6,
0x3b88bbc3,0xbb77393a,0x356433c6,0x35c2ba0f,0xbba83a2f,0x3b50ba0f,0x34a5b913,0xb67c393a,0xbb0e3bf6,0x3be2bbf1,0xb78b2e46,0x31792fd6,
0xb4a53913,0x39cbbb25,0xbba83a2f,0x3984b732,0x378bae46,0x3303b7e3,0xbb0e3bf6,0x3bcebaf6,0xbadd39ed,0x3a4fb9cb,0x381db95f,0xb8ec3984,
0xbbea3b88,0x3b25bac2,0x30b2b564,0xb7323848,0xbbc33bfe,0x3bb6bb77,0xb3c62a48,0xb44435c2,0xba6d3b3b,0x3bfabbe2,0xb8c436d7,0xacb53179,
0xb9a839a8,0x38ecb984,0x39a8b9a8,0xba4f39cb,0xb9a839a8,0x3732b848,0x39a8b9a8,0xbb253ac2,0xb9a839a8,0x3444b5c2,0x39a8b9a8,0xbbb63b77,
0xb9a839a8,0x2cb5b179,0x39a8b9a8,0xbbfa3be2,0xb81d395f,0x367cb93a,0x3addb9ed,0xbb503a0f,0xb0b23564,0xb179afd6,0x3beabb88,0xbbe23bf1,
0x33c6aa48,0xb9843732,0x3bc3bbfe,0xb9cb3b25,0x38c4b6d7,0xbbce3af6,0x3a6dbb3b,0xb30337e3,0xb4a53913,0x3179b8ec,0x3ba8ba2f,0xbbe23a4f,
0x378bae46,0xb9cb3505,0x3b0ebbf6,0xb9843b99,0x3ba8ba2f,0xbbce3bb6,0x34a5b913,0x33033444,0x3b0ebbf6,0xb5c23a0f,0xb78b2e46,0x3b77b93a,
0xaa4838c4,0xacb5b89b,0x3bfeba6d,0xbbfa3a8a,0x3b3bb81d,0xbbf13984,0x36d7badd,0xafd639cb,0x39edbbea,0xb5053ac2,0xb95f30b2,0x3b99b848,
0xb564b3c6,0x3af6b5c2,0xbb883bc3,0x37e3bb77,0x323e3872,0xb505b848,0x3bd9baa7,0xbb993ac2,0x3bd9baa7,0xbaf63b77,0xb23eb872,0x37e335c2,
0xb23eb872,0x393a3179,0xbbd93aa7,0x3a0fbbe2,0xbbd93aa7,0x38ecbbff,0x323e3872,0xba4f2648,0x36d7381d,0xb848b7e3,0x3b3bbadd,0xbac23af6,
0x395fbbea,0xb67c3bfa,0xb9edb0b2,0x3b50acb5,0xbb8833c6,0x3be2b8ec,0xb5643bc3,0xb179ba4f,0x2a483a6d,0xb984b505,0x3bfeb8c4,0xb9cb3b99,
0x3913378b,0xb9cbb732,0x3a2fbb0e,0xb9843b25,0x2e46bba8,0x33033af6,0xbbf634a5,0x3bceb7e3,0xba2f3b0e,0x35c2bbfa,0x3913378b,0xbb77acb5,
0x3bf6b4a5,0xba8a3a4f,0x2e46bba8,0x389b38ec,0x3a6d36d7,0xbaf6b67c,0x38c4bb3b,0xb7e33b50,0xb81db9ed,0x3a0f389b,0xbadd395f,0x393aba8a,
0x30b23b88,0xb8ecb9cb,0x3beab564,0xba4f3984,0x33c6bbfe,0x37323ac2,0xbbc3aa48,0x3b25b848,0x3b64361f,0xbbb6b5c2,0x361fbb64,0xb4443b77,
0xbb64b61f,0x3bfa3179,0xb61f3b64,0x2cb5bbe2,0x3b64361f,0xbbf12648,0x361fbb64,0x2fd63bff,0xbb64b61f,0x3b99b303,0xb61f3b64,0xb505bbce,
0x3bea3564,0xbbffb505,0x30b2bb88,0xa6483b99,0xbbc32a48,0x3ac2b444,0x33c63bfe,0xb848bbb6,0x3a6db6d7,0xb67c3a0f,0xb8c4bb3b,0x3b50393a,
0xb81d39ed,0xb179bbf1,0x3add395f,0xbbe2afd6,0x3bf634a5,0xbbceb444,0xae46bba8,0x33033bb6,0xb913378b,0x35c2b93a,0x3a2f3b0e,0xbb77ba0f,
0xae46bba8,0x389b3bf1,0xbbf6b4a5,0x3a8aafd6,0x3a2f3b0e,0xbbffb732,0x3913b78b,0x26483b25,0x3b8833c6,0xbb25b303,0xb564bbc3,0x37323bce,
0xaa483a6d,0xb444bb50,0x3bfe38c4,0xbbb6b67c,0xbb3bbadd,0x3bfa389b,0xb6d7381d,0xacb5ba8a,0x39edb0b2,0xafd63984,0xb95fbbea,0x3bf139cb,
0x3aa7323e,0xba0fb179,0xb872bbd9,0x393a3be2,0x38723bd9,0xba4fbbff,0x3aa7323e,0xb8ec2648,0xbaa7b23e,0x3732b303,0x38723bd9,0xbb25bbce,
0xb872bbd9,0x3bb63b50,0xbaa7b23e,0x3444b67c,0x395f30b2,0xb89bafd6,0xb9edbbea,0x3a8a3bf1,0x3b883bc3,0xbbffbb25,0x3564b3c6,0xa6483732,
0x2a4838c4,0xb848baf6,0x3bfe3a6d,0xbac2b7e3,0xbb3bb81d,0x367cacb5,0x36d73add,0xbb50bbfa,0x378b2e46,0xb5c2acb5,0xbb0ebbf6,0x3b773bfa,
0x3ba83a2f,0xba8ab8ec,0xb4a5b913,0x389b3a4f,0x3b0e3bf6,0xbbffbb99,0x378b2e46,0x26483505,0x34a53913,0xbac2bbb6,0x3ba83a2f,0xb848b444,
0x33c62a48,0xafd6a648,0xbbc3bbfe,0x3bf13bff,0x38c436d7,0xb505b303,0xba6dbb3b,0x3b993bce,0x3add39ed,0xb7e3b67c,0xb81db95f,0x3af63b50,
0x3bea3b88,0xb93ab89b,0xb0b2b564,0x3a0f3a8a,0x3c003c00,0x38ec3984,0,0xba4fb9cb,0x3c003c00,0x37323848,0,0xbb25bac2,
0x3c003c00,0x344435c2,0,0xbbb6bb77,0x3c003c00,0x2cb53179,0,0xbbfabbe2,0xb3c6aa48,0xbb50ba0f,0xbbc3bbfe,0xb67cb93a,
0xb8c4b6d7,0xbbe2bbf1,0xba6dbb3b,0x3179afd6,0xbaddb9ed,0xb9cbbb25,0xb81db95f,0x39843732,0xbbeabb88,0xb303b7e3,0xb0b2b564,0x3bce3af6,
0xbb0ebbf6,0xb179b8ec,0x378b2e46,0x3be23a4f,0xb4a5b913,0x39cb3505,0x3ba83a2f,0x39843b99,0x378b2e46,0x3bce3bb6,0x3b0e3bf6,0xb3033444,
0x3ba83a2f,0x35c23a0f,0x34a53913,0xbb77b93a,0x395f30b2,0x3bfa3a8a,0x39ed3bea,0xacb5389b,0x3b883bc3,0x2fd639cb,0xb56433c6,0xbbf1b984,
0x2a4838c4,0xbb99b848,0xbbfeba6d,0xb505bac2,0xbb3bb81d,0xb7e3bb77,0xb6d7badd,0x3af635c2,0x38723bd9,0xb5053848,0xbaa7b23e,0xbb99bac2,
0xbaa7b23e,0xbaf6bb77,0xb872bbd9,0x37e3b5c2,0xb872bbd9,0x393ab179,0x3aa7323e,0x3a0f3be2,0x3aa7323e,0x38ec3bff,0x38723bd9,0xba4fa648,
0xbb88b3c6,0xbac2baf6,0xb564bbc3,0x3848b7e3,0x2a48ba6d,0x3b502cb5,0x3bfe38c4,0x367c3bfa,0x3b3b3add,0xb1793a4f,0xb6d7381d,0xbbe2b8ec,
0xb9ed30b2,0xb9cbbb99,0xb95fbbea,0x3984b505,0xae46bba8,0x39cbb732,0x3bf634a5,0x39843b25,0x3a2f3b0e,0xb3033af6,0xb913378b,0xbbceb7e3,
0xbbf6b4a5,0xb5c2bbfa,0xae46bba8,0x3b77acb5,0x3913b78b,0x3a8a3a4f,0x3a2f3b0e,0xb89b38ec,0x3bea3564,0x37e33b50,0xb0b23b88,0xbaf6367c,
0xbbc32a48,0xb93aba8a,0xb3c6bbfe,0x3a0fb89b,0x3a6db6d7,0x3a4f3984,0x38c43b3b,0xb8ec39cb,0xb81d39ed,0xbb25b848,0xbaddb95f,0x3732bac2,
0xb61f3b64,0xbbb635c2,0xbb64b61f,0xb444bb77,0x361fbb64,0x3bfab179,0x3b64361f,0x2cb53be2,0xb61f3b64,0xbbf1a648,0xbb64b61f,0x2fd6bbff,
0x361fbb64,0x3b993303,0x3b64361f,0xb5053bce,0xba6db6d7,0xa648bb99,0x38c4bb3b,0x3bffb505,0x381d39ed,0xb8483bb6,0xbadd395f,0xbac2b444,
0xb0b2bb88,0x3b50b93a,0x3beab564,0x367c3a0f,0xb3c63bfe,0xbbe22fd6,0xbbc3aa48,0x3179bbf1,0x3a2fbb0e,0x3bceb444,0x3913378b,0xb3033bb6,
0xbbf634a5,0xb5c2b93a,0x2e46bba8,0x3b77ba0f,0x3913378b,0xb89b3bf1,0xba2f3b0e,0xba8aafd6,0x2e46bba8,0x3bffb732,0x3bf6b4a5,0xa6483b25,
0x36d7381d,0xb7323bce,0xbb3b3add,0xbb253303,0x395fbbea,0x3bb6b67c,0x39ed30b2,0xb4443b50,0xbb8833c6,0x2cb5ba8a,0x3564bbc3,0x3bfab89b,
0x2a483a6d,0xbbf139cb,0xbbfe38c4,0xafd6b984,0xbbd93aa7,0xba0f3179,0xb23eb872,0x393abbe2,0x323e3872,0xba4f3bff,0xbbd93aa7,0xb8eca648,
0x3bd9baa7,0x37323303,0x323e3872,0xbb253bce,0xb23eb872,0x3bb6bb50,0x3bd9baa7,0x3444367c,0x2a48b8c4,0x3a8abbf1,0x3bfeba6d,0x389bafd6,
0xbb3b381d,0xa648b732,0x36d7badd,0x3bffbb25,0xb9ed3bea,0xbac237e3,0xb95f30b2,0x3848baf6,0x356433c6,0xbb503bfa,0xbb883bc3,0xb67cacb5,
0x3ba8ba2f,0x35c2acb5,0xb4a53913,0xbb773bfa,0x3b0ebbf6,0x3a8ab8ec,0x378bae46,0xb89b3a4f,0x34a5b913,0x3bffbb99,0x3ba8ba2f,0xa6483505,
0xb78b2e46,0x3ac2bbb6,0x3b0ebbf6,0x3848b444,0xb81d395f,0xbbf13bff,0xbadd39ed,0xafd62648,0xb0b23564,0xbb993bce,0xbbea3b88,0xb5053303,
0x33c6aa48,0xbaf63b50,0xbbc33bfe,0xb7e3367c,0x38c4b6d7,0xba0f3a8a,0xba6d3b3b,0xb93a389b,0xb9a839a8,0x2fd6a648,0x39a8b9a8,0x3bf1bbff,
0xb9a839a8,0x3505b303,0x39a8b9a8,0x3b99bbce,0xb9a839a8,0x37e3b67c,0x39a8b9a8,0x3af6bb50,0xb9a839a8,0x393ab89b,0x39a8b9a8,0x3a0fba8a,
0x3addb9ed,0x3b77bbfa,0x381db95f,0xb5c22cb5,0x3beabb88,0x389bba4f,0x30b2b564,0xba8a38ec,0x3bc3bbfe,0x2648b505,0xb3c62a48,0xbbff3b99,
0x3a6dbb3b,0xb8483444,0xb8c436d7,0xbac23bb6,0x34a5b913,0xb89b2fd6,0xbba83a2f,0xba8a3bf1,0xb78b2e46,0xbbff3b25,0xbb0e3bf6,0x26483732,
0xbba83a2f,0xb8483af6,0xb4a53913,0x3ac2b7e3,0xbb0e3bf6,0x367c2cb5,0x378bae46,0x3b50bbfa,0xbbfe3a6d,0xb93a3be2,0xaa4838c4,0x3a0fb179,
0xb6d73add,0x38ec2648,0x3b3bb81d,0x3a4fbbff,0x395fb0b2,0x3b25bbce,0x39edbbea,0xb732b303,0x3b88bbc3,0xb444b67c,0xb564b3c6,0xbbb63b50,
0x323e3872,0x3b25b303,0x3bd9baa7,0x3732bbce,0x3bd9baa7,0x3444bb50,0xb23eb872,0xbbb6367c,0xb23eb872,0xbbfa389b,0xbbd93aa7,0xacb53a8a,
0xbbd93aa7,0x2fd63984,0x323e3872,0x3bf1b9cb,0x3b3bbadd,0x3303bbb6,0xb6d7b81d,0xbbce3444,0xb9edb0b2,0xbb773a0f,0xb95f3bea,0x35c2393a,
0xb5643bc3,0x3a8a2fd6,0x3b88b3c6,0x389bbbf1,0x3bfeb8c4,0x2648bb25,0xaa48ba6d,0xbbff3732,0xb913b78b,0xbbff3505,0xba2f3b0e,0x26483b99,
0xae463ba8,0x3ac23444,0x3bf6b4a5,0x3848bbb6,0x3a2fbb0e,0xb67cba0f,0xb913b78b,0xbb50393a,0xbbf634a5,0xb1793bf1,0xae463ba8,0x3be2afd6,
0xb8c43b3b,0x34443b77,0x3a6d36d7,0x3bb6b5c2,0x3addb95f,0xacb5bbe2,0xb81db9ed,0xbbfa3179,0xbbea3564,0xafd63bff,0x30b23b88,0x3bf12648,
0x3bc32a48,0x3505bbce,0x33c6bbfe,0xbb99b303,0x3b64361f,0x3af6b67c,0x361fbb64,0xb7e3bb50,0xbb64b61f,0xba0f389b,0xb61f3b64,0x393a3a8a,
0x3b64361f,0x38ecb9cb,0x361fbb64,0xba4fb984,0xbb64b61f,0xb7323ac2,0xb61f3b64,0x3b253848,0x30b2bb88,0xb984bb25,0xbbeab564,0xb9cb3732,
0x33c63bfe,0x3bce37e3,0x3bc3aa48,0x3303baf6,0xb8c4bb3b,0xbb772cb5,0xba6d36d7,0x35c23bfa,0x3add395f,0x389bb8ec,0x381db9ed,0xba8aba4f,
0xbbf6b4a5,0xb84837e3,0x2e463ba8,0x3ac23af6,0x3913b78b,0xb67cbbfa,0xba2fbb0e,0xbb50acb5,0x2e463ba8,0x3be238ec,0x3bf634a5,0x3179ba4f,
0xba2fbb0e,0xb9843505,0xb913378b,0x39cb3b99,0x35643bc3,0x3b993ac2,0x3b8833c6,0x3505b848,0xbbfeb8c4,0xb7e335c2,0xaa483a6d,0x3af63b77,
0x36d7b81d,0xba0fbbe2,0xbb3bbadd,0xb93a3179,0x395f3bea,0x3a4f2648,0x39edb0b2,0xb8ecbbff,0x3aa7323e,0x2cb5b89b,0xb872bbd9,0xbbfaba8a,
0x38723bd9,0x3bf13984,0x3aa7323e,0xafd6b9cb,0xbaa7b23e,0x35053ac2,0x38723bd9,0x3b993848,0xb872bbd9,0xbaf6b5c2,0xbaa7b23e,0x37e33b77,
0xb9edbbea,0xbbe2ba4f,0xb95fb0b2,0x317938ec,0x3564b3c6,0xb984bb99,0xbb88bbc3,0xb9cbb505,0x3bfe3a6d,0x3303b444,0xaa48b8c4,0xbbcebbb6,
0x36d73add,0x3b77393a,0x3b3b381d,0xb5c2ba0f,0xb78bae46,0x367c393a,0x3b0e3bf6,0x3b503a0f,0xbba8ba2f,0xb1792fd6,0x34a53913,0x3be23bf1,
0xbb0ebbf6,0xb984b732,0xb78bae46,0x39cb3b25,0xb4a5b913,0xbbcebaf6,0xbba8ba2f,0x330337e3,0x3bc33bfe,0x3a4f39cb,0x33c62a48,0xb8ecb984,
0x3a6d3b3b,0x3b253ac2,0x38c436d7,0xb732b848,0x381d395f,0x3bb63b77,0x3add39ed,0xb444b5c2,0x30b23564,0x3bfa3be2,0x3bea3b88,0xacb5b179,
0x3c003c00,0xb8ecb984,0,0x3a4f39cb,0x3c003c00,0xb732b848,0,0x3b253ac2,0x3c003c00,0xb444b5c2,0,0x3bb63b77,
0x3c003c00,0xacb5b179,0,0x3bfa3be2,0xb3c6aa48,0x3b503a0f,0xbbc3bbfe,0x367c393a,0xb8c4b6d7,0x3be23bf1,0xba6dbb3b,0xb1792fd6,
0xbaddb9ed,0x39cb3b25,0xb81db95f,0xb984b732,0xbbeabb88,0x330337e3,0xb0b2b564,0xbbcebaf6,0xbb0ebbf6,0x317938ec,0x378b2e46,0xbbe2ba4f,
0xb4a5b913,0xb9cbb505,0x3ba83a2f,0xb984bb99,0x378b2e46,0xbbcebbb6,0x3b0e3bf6,0x3303b444,0x3ba83a2f,0xb5c2ba0f,0x34a53913,0x3b77393a,
0x395f30b2,0xbbfaba8a,0x39ed3bea,0x2cb5b89b,0x3b883bc3,0xafd6b9cb,0xb56433c6,0x3bf13984,0x2a4838c4,0x3b993848,0xbbfeba6d,0x35053ac2,
0xbb3bb81d,0x37e33b77,0xb6d7badd,0xbaf6b5c2,0x38723bd9,0x3505b848,0xbaa7b23e,0x3b993ac2,0xbaa7b23e,0x3af63b77,0xb872bbd9,0xb7e335c2,
0xb872bbd9,0xb93a3179,0x3aa7323e,0xba0fbbe2,0x3aa7323e,0xb8ecbbff,0x38723bd9,0x3a4f2648,0xbb88b3c6,0x3ac23af6,0xb564bbc3,0xb84837e3,
0x2a48ba6d,0xbb50acb5,0x3bfe38c4,0xb67cbbfa,0x3b3b3add,0x3179ba4f,0xb6d7381d,0x3be238ec,0xb9ed30b2,0x39cb3b99,0xb95fbbea,0xb9843505,
0xae46bba8,0xb9cb3732,0x3bf634a5,0xb984bb25,0x3a2f3b0e,0x3303baf6,0xb913378b,0x3bce37e3,0xbbf6b4a5,0x35c23bfa,0xae46bba8,0xbb772cb5,
0x3913b78b,0xba8aba4f,0x3a2f3b0e,0x389bb8ec,0x3bea3564,0xb7e3bb50,0xb0b23b88,0x3af6b67c,0xbbc32a48,0x393a3a8a,0xb3c6bbfe,0xba0f389b,
0x3a6db6d7,0xba4fb984,0x38c43b3b,0x38ecb9cb,0xb81d39ed,0x3b253848,0xbaddb95f,0xb7323ac2,0xb61f3b64,0x3bb6b5c2,0xbb64b61f,0x34443b77,
0x361fbb64,0xbbfa3179,0x3b64361f,0xacb5bbe2,0xb61f3b64,0x3bf12648,0xbb64b61f,0xafd63bff,0x361fbb64,0xbb99b303,0x3b64361f,0x3505bbce,
0xba6db6d7,0x26483b99,0x38c4bb3b,0xbbff3505,0x381d39ed,0x3848bbb6,0xbadd395f,0x3ac23444,0xb0b2bb88,0xbb50393a,0x3beab564,0xb67cba0f,
0xb3c63bfe,0x3be2afd6,0xbbc3aa48,0xb1793bf1,0x3a2fbb0e,0xbbce3444,0x3913378b,0x3303bbb6,0xbbf634a5,0x35c2393a,0x2e46bba8,0xbb773a0f,
0x3913378b,0x389bbbf1,0xba2f3b0e,0x3a8a2fd6,0x2e46bba8,0xbbff3732,0x3bf6b4a5,0x2648bb25,0x36d7381d,0x3732bbce,0xbb3b3add,0x3b25b303,
0x395fbbea,0xbbb6367c,0x39ed30b2,0x3444bb50,0xbb8833c6,0xacb53a8a,0x3564bbc3,0xbbfa389b,0x2a483a6d,0x3bf1b9cb,0xbbfe38c4,0x2fd63984,
0xbbd93aa7,0x3a0fb179,0xb23eb872,0xb93a3be2,0x323e3872,0x3a4fbbff,0xbbd93aa7,0x38ec2648,0x3bd9baa7,0xb732b303,0x323e3872,0x3b25bbce,
0xb23eb872,0xbbb63b50,0x3bd9baa7,0xb444b67c,0x2a48b8c4,0xba8a3bf1,0x3bfeba6d,0xb89b2fd6,0xbb3b381d,0x26483732,0x36d7badd,0xbbff3b25,
0xb9ed3bea,0x3ac2b7e3,0xb95f30b2,0xb8483af6,0x356433c6,0x3b50bbfa,0xbb883bc3,0x367c2cb5,0x3ba8ba2f,0xb5c22cb5,0xb4a53913,0x3b77bbfa,
0x3b0ebbf6,0xba8a38ec,0x378bae46,0x389bba4f,0x34a5b913,0xbbff3b99,0x3ba8ba2f,0x2648b505,0xb78b2e46,0xbac23bb6,0x3b0ebbf6,0xb8483444,
0xb81d395f,0x3bf1bbff,0xbadd39ed,0x2fd6a648,0xb0b23564,0x3b99bbce,0xbbea3b88,0x3505b303,0x33c6aa48,0x3af6bb50,0xbbc33bfe,0x37e3b67c,
0x38c4b6d7,0x3a0fba8a,0xba6d3b3b,0x393ab89b,0xb9a839a8,0xafd62648,0x39a8b9a8,0xbbf13bff,0xb9a839a8,0xb5053303,0x39a8b9a8,0xbb993bce,
0xb9a839a8,0xb7e3367c,0x39a8b9a8,0xbaf63b50,0xb9a839a8,0xb93a389b,0x39a8b9a8,0xba0f3a8a,0x3addb9ed,0xbb773bfa,0x381db95f,0x35c2acb5,
0x3beabb88,0xb89b3a4f,0x30b2b564,0x3a8ab8ec,0x3bc3bbfe,0xa6483505,0xb3c62a48,0x3bffbb99,0x3a6dbb3b,0x3848b444,0xb8c436d7,0x3ac2bbb6,
0x34a5b913,0x389bafd6,0xbba83a2f,0x3a8abbf1,0xb78b2e46,0x3bffbb25,0xbb0e3bf6,0xa648b732,0xbba83a2f,0x3848baf6,0xb4a53913,0xbac237e3,
0xbb0e3bf6,0xb67cacb5,0x378bae46,0xbb503bfa,0xbbfe3a6d,0x393abbe2,0xaa4838c4,0xba0f3179,0xb6d73add,0xb8eca648,0x3b3bb81d,0xba4f3bff,
0x395fb0b2,0xbb253bce,0x39edbbea,0x37323303,0x3b88bbc3,0x3444367c,0xb564b3c6,0x3bb6bb50,0x323e3872,0xbb253303,0x3bd9baa7,0xb7323bce,
0x3bd9baa7,0xb4443b50,0xb23eb872,0x3bb6b67c,0xb23eb872,0x3bfab89b,0xbbd93aa7,0x2cb5ba8a,0xbbd93aa7,0xafd6b984,0x323e3872,0xbbf139cb,
0x3b3bbadd,0xb3033bb6,0xb6d7b81d,0x3bceb444,0xb9edb0b2,0x3b77ba0f,0xb95f3bea,0xb5c2b93a,0xb5643bc3,0xba8aafd6,0x3b88b3c6,0xb89b3bf1,
0x3bfeb8c4,0xa6483b25,0xaa48ba6d,0x3bffb732,0xb913b78b,0x3bffb505,0xba2f3b0e,0xa648bb99,0xae463ba8,0xbac2b444,0x3bf6b4a5,0xb8483bb6,
0x3a2fbb0e,0x367c3a0f,0xb913b78b,0x3b50b93a,0xbbf634a5,0x3179bbf1,0xae463ba8,0xbbe22fd6,0xb8c43b3b,0xb444bb77,0x3a6d36d7,0xbbb635c2,
0x3addb95f,0x2cb53be2,0xb81db9ed,0x3bfab179,0xbbea3564,0x2fd6bbff,0x30b23b88,0xbbf1a648,0x3bc32a48,0xb5053bce,0x33c6bbfe,0x3b993303,
0x3b64361f,0xbaf6367c,0x361fbb64,0x37e33b50,0xbb64b61f,0x3a0fb89b,0xb61f3b64,0xb93aba8a,0x3b64361f,0xb8ec39cb,0x361fbb64,0x3a4f3984,
0xbb64b61f,0x3732bac2,0xb61f3b64,0xbb25b848,0x30b2bb88,0x39843b25,0xbbeab564,0x39cbb732,0x33c63bfe,0xbbceb7e3,0x3bc3aa48,0xb3033af6,
0xb8c4bb3b,0x3b77acb5,0xba6d36d7,0xb5c2bbfa,0x3add395f,0xb89b38ec,0x381db9ed,0x3a8a3a4f,0xbbf6b4a5,0x3848b7e3,0x2e463ba8,0xbac2baf6,
0x3913b78b,0x367c3bfa,0xba2fbb0e,0x3b502cb5,0x2e463ba8,0xbbe2b8ec,0x3bf634a5,0xb1793a4f,0xba2fbb0e,0x3984b505,0xb913378b,0xb9cbbb99,
0x35643bc3,0xbb99bac2,0x3b8833c6,0xb5053848,0xbbfeb8c4,0x37e3b5c2,0xaa483a6d,0xbaf6bb77,0x36d7b81d,0x3a0f3be2,0xbb3bbadd,0x393ab179,
0x395f3bea,0xba4fa648,0x39edb0b2,0x38ec3bff,0x3aa7323e,0xacb5389b,0xb872bbd9,0x3bfa3a8a,0x38723bd9,0xbbf1b984,0x3aa7323e,0x2fd639cb,
0xbaa7b23e,0xb505bac2,0x38723bd9,0xbb99b848,0xb872bbd9,0x3af635c2,0xbaa7b23e,0xb7e3bb77,0xb9edbbea,0x3be23a4f,0xb95fb0b2,0xb179b8ec,
0x3564b3c6,0x39843b99,0xbb88bbc3,0x39cb3505,0x3bfe3a6d,0xb3033444,0xaa48b8c4,0x3bce3bb6,0x36d73add,0xbb77b93a,0x3b3b381d,0x35c23a0f,
0xb78bae46,0xb67cb93a,0x3b0e3bf6,0xbb50ba0f,0xbba8ba2f,0x3179afd6,0x34a53913,0xbbe2bbf1,0xbb0ebbf6,0x39843732,0xb78bae46,0xb9cbbb25,
0xb4a5b913,0x3bce3af6,0xbba8ba2f,0xb303b7e3,0x3bc33bfe,0xba4fb9cb,0x33c62a48,0x38ec3984,0x3a6d3b3b,0xbb25bac2,0x38c436d7,0x37323848,
0x381d395f,0xbbb6bb77,0x3add39ed,0x344435c2,0x30b23564,0xbbfabbe2,0x3bea3b88,0x2cb53179,0x3c003c00,0xafd6a648,0,0xbbf1bbff,
0x3c003c00,0xb505b303,0,0xbb99bbce,0x3c003c00,0xb7e3b67c,0,0xbaf6bb50,0x3c003c00,0xb93ab89b,0,0xba0fba8a,
0xbbc3bbfe,0x35c22cb5,0x33c62a48,0x3b773bfa,0xba6dbb3b,0x3a8a38ec,0x38c436d7,0x389b3a4f,0xb81db95f,0x3bff3b99,0x3add39ed,0x26483505,
0xb0b2b564,0x3ac23bb6,0x3bea3b88,0xb848b444,0x3b0e3bf6,0xb89bafd6,0xb78bae46,0xba8abbf1,0x34a53913,0xbbffbb25,0xbba8ba2f,0x2648b732,
0xb78bae46,0xb848baf6,0xbb0ebbf6,0x3ac237e3,0xbba8ba2f,0x367cacb5,0xb4a5b913,0x3b503bfa,0xb9edbbea,0x3a0f3179,0x395f30b2,0x393a3be2,
0x3564b3c6,0x3a4f3bff,0x3b883bc3,0xb8ec2648,0x3bfe3a6d,0xb7323303,0x2a4838c4,0xbb25bbce,0x36d73add,0xbbb6bb50,0xbb3bb81d,0x3444b67c,
0x38723bd9,0xbb25b303,0xbaa7b23e,0xb732bbce,0xbaa7b23e,0xb444bb50,0xb872bbd9,0x3bb6367c,0xb872bbd9,0x3bfa389b,0x3aa7323e,0x2cb53a8a,
0x3aa7323e,0xafd63984,0x38723bd9,0xbbf1b9cb,0xb564bbc3,0x3bce3444,0x3b8833c6,0x33033bb6,0x3bfe38c4,0xb5c2393a,0xaa483a6d,0xbb77ba0f,
0xb6d7381d,0xb89bbbf1,0xbb3bbadd,0x3a8aafd6,0xb95fbbea,0x3bff3732,0x39edb0b2,0x26483b25,0x2e463ba8,0xbbffb505,0xbbf6b4a5,0x2648bb99,
0xba2fbb0e,0x3ac2b444,0x3913b78b,0x38483bb6,0x3bf634a5,0xb67c3a0f,0x2e463ba8,0xbb50b93a,0xb913378b,0xb179bbf1,0xba2fbb0e,0x3be22fd6,
0x30b2bb88,0x3bb635c2,0x3bea3564,0xb4443b77,0x33c63bfe,0xbbfab179,0xbbc32a48,0x2cb5bbe2,0xb8c4bb3b,0x3bf1a648,0x3a6db6d7,0x2fd63bff,
0x3add395f,0xbb993303,0xb81d39ed,0xb505bbce,0xb61f3b64,0xbaf6b67c,0xbb64b61f,0x37e3bb50,0x361fbb64,0x3a0f389b,0x3b64361f,0xb93a3a8a,
0xb61f3b64,0xb8ecb9cb,0xbb64b61f,0x3a4fb984,0x361fbb64,0x37323ac2,0x3b64361f,0xbb253848,0x38c4bb3b,0x39cb3732,0x3a6d36d7,0xb9843b25,
0xbadd395f,0xb303baf6,0xb81db9ed,0x3bceb7e3,0x3beab564,0xb5c23bfa,0x30b23b88,0xbb77acb5,0xbbc3aa48,0x3a8aba4f,0x33c6bbfe,0x389b38ec,
0xba2f3b0e,0xb848b7e3,0xb913b78b,0x3ac2baf6,0x3bf6b4a5,0xb67c3bfa,0xae463ba8,0xbb502cb5,0xb913b78b,0x3be2b8ec,0x3a2fbb0e,0x31793a4f,
0xae463ba8,0xb984b505,0xbbf634a5,0x39cbbb99,0x3b3bbadd,0x35053848,0x36d7381d,0xbb993ac2,0xb9edb0b2,0x3af6bb77,0x395fbbea,0x37e335c2,
0xb5643bc3,0xb93ab179,0xbb8833c6,0x3a0fbbe2,0x3bfeb8c4,0xb8ec3bff,0x2a483a6d,0xba4f2648,0xbbd93aa7,0xacb5b89b,0xb23eb872,0x3bfaba8a,
0x323e3872,0xbbf13984,0xbbd93aa7,0x2fd6b9cb,0x3bd9baa7,0xb5053ac2,0x323e3872,0xbb993848,0xb23eb872,0x3af6b5c2,0x3bd9baa7,0xb7e33b77,
0x3bfeba6d,0xb17938ec,0xaa4838c4,0xbbe23a4f,0x36d7badd,0x39cbb505,0x3b3bb81d,0xb9843b99,0xb95f30b2,0x3bcebbb6,0x39edbbea,0x33033444,
0xbb883bc3,0x35c2ba0f,0xb564b3c6,0x3b77b93a,0xbba83a2f,0x367cb93a,0x34a5b913,0x3b50ba0f,0xbb0e3bf6,0xb179afd6,0xb78b2e46,0x3be2bbf1,
0xb4a53913,0xb9843732,0xbba83a2f,0x39cbbb25,0x378bae46,0xbbce3af6,0xbb0e3bf6,0x3303b7e3,0x3addb9ed,0xb8ec3984,0xb81d395f,0xba4f39cb,
0x3beabb88,0xb7323848,0xb0b23564,0xbb253ac2,0x3bc3bbfe,0xb44435c2,0x33c6aa48,0xbbb63b77,0x3a6dbb3b,0xacb53179,0x38c4b6d7,0xbbfa3be2,
0xb9a839a8,0x3a4fb9cb,0x39a8b9a8,0x38ecb984,0xb9a839a8,0x3b25bac2,0x39a8b9a8,0x3732b848,0xb9a839a8,0x3bb6bb77,0x39a8b9a8,0x3444b5c2,
0xb9a839a8,0x3bfabbe2,0x39a8b9a8,0x2cb5b179,0x381db95f,0xbb503a0f,0xbadd39ed,0xb67c393a,0x30b2b564,0xbbe23bf1,0xbbea3b88,0x31792fd6,
0xb3c62a48,0xb9cb3b25,0xbbc33bfe,0x3984b732,0xb8c436d7,0xb30337e3,0xba6d3b3b,0x3bcebaf6,0xb4a53913,0x3be2ba4f,0x3ba8ba2f,0x3179b8ec,
0x378bae46,0x3984bb99,0x3b0ebbf6,0xb9cb3505,0x3ba8ba2f,0xb303b444,0x34a5b913,0xbbce3bb6,0x3b0ebbf6,0xbb77393a,0xb78b2e46,0xb5c23a0f,
0x2a48b8c4,0xbbfa3a8a,0xbbfe3a6d,0x2cb5389b,0xbb3b381d,0xafd639cb,0xb6d73add,0x3bf1b984,0xb9ed3bea,0x3b99b848,0x395fb0b2,0x3505bac2,
0x356433c6,0x37e3bb77,0x3b88bbc3,0xbaf635c2,0x323e3872,0x3b99bac2,0x3bd9baa7,0xb505b848,0x3bd9baa7,0xb7e3b5c2,0xb23eb872,0xbaf63b77,
0xb23eb872,0xba0f3be2,0xbbd93aa7,0x393a3179,0xbbd93aa7,0x3a4fa648,0x323e3872,0x38ecbbff,0xb6d7b81d,0xbac23af6,0xbb3b3add,0x384837e3,
0xb95f3bea,0x3b50acb5,0x39ed30b2,0x367cbbfa,0x3b88b3c6,0xb179ba4f,0x3564bbc3,0xbbe238ec,0xaa48ba6d,0xb9cb3b99,0xbbfe38c4,0x39843505,
0x3913378b,0x3984bb25,0x3a2fbb0e,0xb9cbb732,0x2e46bba8,0xbbce37e3,0xbbf634a5,0x33033af6,0xba2f3b0e,0x3b772cb5,0x3913378b,0x35c2bbfa,
0x3bf6b4a5,0xb89bb8ec,0x2e46bba8,0xba8a3a4f,0xba6db6d7,0xb7e33b50,0xb8c43b3b,0x3af6367c,0x381d39ed,0x393aba8a,0x3addb95f,0xba0fb89b,
0xb0b2bb88,0xba4f3984,0xbbea3564,0x38ec39cb,0xb3c63bfe,0x3b25b848,0x3bc32a48,0xb732bac2,0x3b64361f,0x3444bb77,0x361fbb64,0xbbb6b5c2,
0xbb64b61f,0xacb53be2,0xb61f3b64,0x3bfa3179,0x3b64361f,0xafd6bbff,0x361fbb64,0xbbf12648,0xbb64b61f,0x35053bce,0xb61f3b64,0x3b99b303,
0xbbeab564,0xa6483b99,0xb0b23b88,0x3bff3505,0x3bc3aa48,0xb848bbb6,0xb3c6bbfe,0xbac23444,0xba6d36d7,0x3b50393a,0x38c43b3b,0x367cba0f,
0x381db9ed,0xbbe2afd6,0xbaddb95f,0x31793bf1,0x3bf634a5,0xb303bbb6,0xae46bba8,0xbbceb444,0xb913378b,0x3b773a0f,0x3a2f3b0e,0x35c2b93a,
0xae46bba8,0xba8a2fd6,0xbbf6b4a5,0x389b3bf1,0x3a2f3b0e,0xa648bb25,0x3913b78b,0xbbffb732,0xbb88b3c6,0x37323bce,0x35643bc3,0x3b253303,
0x2a48ba6d,0xbbb6b67c,0xbbfeb8c4,0x34443b50,0x3b3b3add,0xacb5ba8a,0x36d7b81d,0xbbfab89b,0xb9ed30b2,0x3bf139cb,0x395f3bea,0x2fd6b984,
0x3aa7323e,0xb93abbe2,0xb872bbd9,0xba0fb179,0x38723bd9,0x38eca648,0x3aa7323e,0xba4fbbff,0xbaa7b23e,0x3b253bce,0x38723bd9,0x3732b303,
0xb872bbd9,0xb444367c,0xbaa7b23e,0x3bb63b50,0xb95fb0b2,0x3a8a3bf1,0x39ed3bea,0x389b2fd6,0xbb88bbc3,0xa6483732,0xb56433c6,0x3bff3b25,
0xaa48b8c4,0xbac2b7e3,0xbbfeba6d,0x38483af6,0x3b3b381d,0xbb50bbfa,0xb6d7badd,0xb67c2cb5,0x378b2e46,0xbb77bbfa,0xbb0ebbf6,0xb5c2acb5,
0x3ba83a2f,0xb89bba4f,0xb4a5b913,0xba8ab8ec,0x3b0e3bf6,0xa648b505,0x378b2e46,0xbbffbb99,0x34a53913,0x38483444,0x3ba83a2f,0xbac2bbb6,
0xb3c6aa48,0x3bf13bff,0x3bc33bfe,0x2fd62648,0xb8c4b6d7,0x3b993bce,0x3a6d3b3b,0x35053303,0xbaddb9ed,0x3af63b50,0x381d395f,0x37e3367c,
0xbbeabb88,0x3a0f3a8a,0x30b23564,0x393a389b,0x3c003c00,0x2fd62648,0,0x3bf13bff,0x3c003c00,0x35053303,0,0x3b993bce,
0x3c003c00,0x37e3367c,0,0x3af63b50,0x3c003c00,0x393a389b,0,0x3a0f3a8a,0xbbc3bbfe,0xb5c2acb5,0x33c62a48,0xbb77bbfa,
0xba6dbb3b,0xba8ab8ec,0x38c436d7,0xb89bba4f,0xb81db95f,0xbbffbb99,0x3add39ed,0xa648b505,0xb0b2b564,0xbac2bbb6,0x3bea3b88,0x38483444,
0x3b0e3bf6,0x389b2fd6,0xb78bae46,0x3a8a3bf1,0x34a53913,0x3bff3b25,0xbba8ba2f,0xa6483732,0xb78bae46,0x38483af6,0xbb0ebbf6,0xbac2b7e3,
0xbba8ba2f,0xb67c2cb5,0xb4a5b913,0xbb50bbfa,0xb9edbbea,0xba0fb179,0x395f30b2,0xb93abbe2,0x3564b3c6,0xba4fbbff,0x3b883bc3,0x38eca648,
0x3bfe3a6d,0x3732b303,0x2a4838c4,0x3b253bce,0x36d73add,0x3bb63b50,0xbb3bb81d,0xb444367c,0x38723bd9,0x3b253303,0xbaa7b23e,0x37323bce,
0xbaa7b23e,0x34443b50,0xb872bbd9,0xbbb6b67c,0xb872bbd9,0xbbfab89b,0x3aa7323e,0xacb5ba8a,0x3aa7323e,0x2fd6b984,0x38723bd9,0x3bf139cb,
0xb564bbc3,0xbbceb444,0x3b8833c6,0xb303bbb6,0x3bfe38c4,0x35c2b93a,0xaa483a6d,0x3b773a0f,0xb6d7381d,0x389b3bf1,0xbb3bbadd,0xba8a2fd6,
0xb95fbbea,0xbbffb732,0x39edb0b2,0xa648bb25,0x2e463ba8,0x3bff3505,0xbbf6b4a5,0xa6483b99,0xba2fbb0e,0xbac23444,0x3913b78b,0xb848bbb6,
0x3bf634a5,0x367cba0f,0x2e463ba8,0x3b50393a,0xb913378b,0x31793bf1,0xba2fbb0e,0xbbe2afd6,0x30b2bb88,0xbbb6b5c2,0x3bea3564,0x3444bb77,
0x33c63bfe,0x3bfa3179,0xbbc32a48,0xacb53be2,0xb8c4bb3b,0xbbf12648,0x3a6db6d7,0xafd6bbff,0x3add395f,0x3b99b303,0xb81d39ed,0x35053bce,
0xb61f3b64,0x3af6367c,0xbb64b61f,0xb7e33b50,0x361fbb64,0xba0fb89b,0x3b64361f,0x393aba8a,0xb61f3b64,0x38ec39cb,0xbb64b61f,0xba4f3984,
0x361fbb64,0xb732bac2,0x3b64361f,0x3b25b848,0x38c4bb3b,0xb9cbb732,0x3a6d36d7,0x3984bb25,0xbadd395f,0x33033af6,0xb81db9ed,0xbbce37e3,
0x3beab564,0x35c2bbfa,0x30b23b88,0x3b772cb5,0xbbc3aa48,0xba8a3a4f,0x33c6bbfe,0xb89bb8ec,0xba2f3b0e,0x384837e3,0xb913b78b,0xbac23af6,
0x3bf6b4a5,0x367cbbfa,0xae463ba8,0x3b50acb5,0xb913b78b,0xbbe238ec,0x3a2fbb0e,0xb179ba4f,0xae463ba8,0x39843505,0xbbf634a5,0xb9cb3b99,
0x3b3bbadd,0xb505b848,0x36d7381d,0x3b99bac2,0xb9edb0b2,0xbaf63b77,0x395fbbea,0xb7e3b5c2,0xb5643bc3,0x393a3179,0xbb8833c6,0xba0f3be2,
0x3bfeb8c4,0x38ecbbff,0x2a483a6d,0x3a4fa648,0xbbd93aa7,0x2cb5389b,0xb23eb872,0xbbfa3a8a,0x323e3872,0x3bf1b984,0xbbd93aa7,0xafd639cb,
0x3bd9baa7,0x3505bac2,0x323e3872,0x3b99b848,0xb23eb872,0xbaf635c2,0x3bd9baa7,0x37e3bb77,0x3bfeba6d,0x3179b8ec,0xaa4838c4,0x3be2ba4f,
0x36d7badd,0xb9cb3505,0x3b3bb81d,0x3984bb99,0xb95f30b2,0xbbce3bb6,0x39edbbea,0xb303b444,0xbb883bc3,0xb5c23a0f,0xb564b3c6,0xbb77393a,
0xbba83a2f,0xb67c393a,0x34a5b913,0xbb503a0f,0xbb0e3bf6,0x31792fd6,0xb78b2e46,0xbbe23bf1,0xb4a53913,0x3984b732,0xbba83a2f,0xb9cb3b25,
0x378bae46,0x3bcebaf6,0xbb0e3bf6,0xb30337e3,0x3addb9ed,0x38ecb984,0xb81d395f,0x3a4fb9cb,0x3beabb88,0x3732b848,0xb0b23564,0x3b25bac2,
0x3bc3bbfe,0x3444b5c2,0x33c6aa48,0x3bb6bb77,0x3a6dbb3b,0x2cb5b179,0x38c4b6d7,0x3bfabbe2,0xb9a839a8,0xba4f39cb,0x39a8b9a8,0xb8ec3984,
0xb9a839a8,0xbb253ac2,0x39a8b9a8,0xb7323848,0xb9a839a8,0xbbb63b77,0x39a8b9a8,0xb44435c2,0xb9a839a8,0xbbfa3be2,0x39a8b9a8,0xacb53179,
0x381db95f,0x3b50ba0f,0xbadd39ed,0x367cb93a,0x30b2b564,0x3be2bbf1,0xbbea3b88,0xb179afd6,0xb3c62a48,0x39cbbb25,0xbbc33bfe,0xb9843732,
0xb8c436d7,0x3303b7e3,0xba6d3b3b,0xbbce3af6,0xb4a53913,0xbbe23a4f,0x3ba8ba2f,0xb17938ec,0x378bae46,0xb9843b99,0x3b0ebbf6,0x39cbb505,
0x3ba8ba2f,0x33033444,0x34a5b913,0x3bcebbb6,0x3b0ebbf6,0x3b77b93a,0xb78b2e46,0x35c2ba0f,0x2a48b8c4,0x3bfaba8a,0xbbfe3a6d,0xacb5b89b,
0xbb3b381d,0x2fd6b9cb,0xb6d73add,0xbbf13984,0xb9ed3bea,0xbb993848,0x395fb0b2,0xb5053ac2,0x356433c6,0xb7e33b77,0x3b88bbc3,0x3af6b5c2,
0x323e3872,0xbb993ac2,0x3bd9baa7,0x35053848,0x3bd9baa7,0x37e335c2,0xb23eb872,0x3af6bb77,0xb23eb872,0x3a0fbbe2,0xbbd93aa7,0xb93ab179,
0xbbd93aa7,0xba4f2648,0x323e3872,0xb8ec3bff,0xb6d7b81d,0x3ac2baf6,0xbb3b3add,0xb848b7e3,0xb95f3bea,0xbb502cb5,0x39ed30b2,0xb67c3bfa,
0x3b88b3c6,0x31793a4f,0x3564bbc3,0x3be2b8ec,0xaa48ba6d,0x39cbbb99,0xbbfe38c4,0xb984b505,0x3913378b,0xb9843b25,0x3a2fbb0e,0x39cb3732,
0x2e46bba8,0x3bceb7e3,0xbbf634a5,0xb303baf6,0xba2f3b0e,0xbb77acb5,0x3913378b,0xb5c23bfa,0x3bf6b4a5,0x389b38ec,0x2e46bba8,0x3a8aba4f,
0xba6db6d7,0x37e3bb50,0xb8c43b3b,0xbaf6b67c,0x381d39ed,0xb93a3a8a,0x3addb95f,0x3a0f389b,0xb0b2bb88,0x3a4fb984,0xbbea3564,0xb8ecb9cb,
0xb3c63bfe,0xbb253848,0x3bc32a48,0x37323ac2,0x3b64361f,0xb4443b77,0x361fbb64,0x3bb635c2,0xbb64b61f,0x2cb5bbe2,0xb61f3b64,0xbbfab179,
0x3b64361f,0x2fd63bff,0x361fbb64,0x3bf1a648,0xbb64b61f,0xb505bbce,0xb61f3b64,0xbb993303,0xbbeab564,0x2648bb99,0xb0b23b88,0xbbffb505,
0x3bc3aa48,0x38483bb6,0xb3c6bbfe,0x3ac2b444,0xba6d36d7,0xbb50b93a,0x38c43b3b,0xb67c3a0f,0x381db9ed,0x3be22fd6,0xbaddb95f,0xb179bbf1,
0x3bf634a5,0x33033bb6,0xae46bba8,0x3bce3444,0xb913378b,0xbb77ba0f,0x3a2f3b0e,0xb5c2393a,0xae46bba8,0x3a8aafd6,0xbbf6b4a5,0xb89bbbf1,
0x3a2f3b0e,0x26483b25,0x3913b78b,0x3bff3732,0xbb88b3c6,0xb732bbce,0x35643bc3,0xbb25b303,0x2a48ba6d,0x3bb6367c,0xbbfeb8c4,0xb444bb50,
0x3b3b3add,0x2cb53a8a,0x36d7b81d,0x3bfa389b,0xb9ed30b2,0xbbf1b9cb,0x395f3bea,0xafd63984,0x3aa7323e,0x393a3be2,0xb872bbd9,0x3a0f3179,
0x38723bd9,0xb8ec2648,0x3aa7323e,0x3a4f3bff,0xbaa7b23e,0xbb25bbce,0x38723bd9,0xb7323303,0xb872bbd9,0x3444b67c,0xbaa7b23e,0xbbb6bb50,
0xb95fb0b2,0xba8abbf1,0x39ed3bea,0xb89bafd6,0xbb88bbc3,0x2648b732,0xb56433c6,0xbbffbb25,0xaa48b8c4,0x3ac237e3,0xbbfeba6d,0xb848baf6,
0x3b3b381d,0x3b503bfa,0xb6d7badd,0x367cacb5,0x378b2e46,0x3b773bfa,0xbb0ebbf6,0x35c22cb5,0x3ba83a2f,0x389b3a4f,0xb4a5b913,0x3a8a38ec,
0x3b0e3bf6,0x26483505,0x378b2e46,0x3bff3b99,0x34a53913,0xb848b444,0x3ba83a2f,0x3ac23bb6,0xb3c6aa48,0xbbf1bbff,0x3bc33bfe,0xafd6a648,
0xb8c4b6d7,0xbb99bbce,0x3a6d3b3b,0xb505b303,0xbaddb9ed,0xbaf6bb50,0x381d395f,0xb7e3b67c,0xbbeabb88,0xba0fba8a,0x30b23564,0xb93ab89b,
0x3c003c00,0xba4fb9cb,0,0xb8ecb984,0x3c003c00,0xbb25bac2,0,0xb732b848,0x3c003c00,0xbbb6bb77,0,0xb444b5c2,
0x3c003c00,0xbbfabbe2,0,0xacb5b179,0x33c62a48,0x367c393a,0x3bc33bfe,0xbb50ba0f,0x38c436d7,0xb1792fd6,0x3a6d3b3b,0xbbe2bbf1,
0x3add39ed,0xb984b732,0x381d395f,0xb9cbbb25,0x3bea3b88,0xbbcebaf6,0x30b23564,0xb303b7e3,0xbb0ebbf6,0x3be23a4f,0x378b2e46,0x317938ec,
0xb4a5b913,0x39843b99,0x3ba83a2f,0xb9cbb505,0x378b2e46,0xb3033444,0x3b0e3bf6,0xbbcebbb6,0x3ba83a2f,0xbb77b93a,0x34a53913,0xb5c2ba0f,
0xb95fb0b2,0x2cb5b89b,0xb9edbbea,0x3bfa3a8a,0xbb88bbc3,0x3bf13984,0x3564b3c6,0x2fd639cb,0xaa48b8c4,0x35053ac2,0x3bfe3a6d,0xbb99b848,
0x3b3b381d,0xbaf6b5c2,0x36d73add,0xb7e3bb77,0x38723bd9,0xbb99bac2,0xbaa7b23e,0x3505b848,0xbaa7b23e,0x37e3b5c2,0xb872bbd9,0x3af63b77,
0xb872bbd9,0x3a0f3be2,0x3aa7323e,0xb93a3179,0x3aa7323e,0xba4fa648,0x38723bd9,0xb8ecbbff,0x3b8833c6,0xb84837e3,0x35643bc3,0xbac2baf6,
0xaa483a6d,0xb67cbbfa,0xbbfeb8c4,0x3b502cb5,0xbb3bbadd,0x3be238ec,0x36d7b81d,0xb1793a4f,0x39edb0b2,0xb9843505,0x395f3bea,0xb9cbbb99,
0xae46bba8,0x39843b25,0x3bf634a5,0xb9cb3732,0x3a2f3b0e,0xbbceb7e3,0xb913378b,0x3303baf6,0xbbf6b4a5,0x3b77acb5,0xae46bba8,0x35c23bfa,
0x3913b78b,0xb89b38ec,0x3a2f3b0e,0xba8aba4f,0xbbeab564,0x3af6b67c,0x30b2bb88,0x37e33b50,0x3bc3aa48,0xba0f389b,0x33c63bfe,0xb93aba8a,
0xba6d36d7,0x38ecb9cb,0xb8c4bb3b,0x3a4f3984,0x381db9ed,0xb7323ac2,0x3add395f,0xbb25b848,0xb61f3b64,0xb444bb77,0xbb64b61f,0x3bb6b5c2,
0x361fbb64,0x2cb53be2,0x3b64361f,0xbbfa3179,0xb61f3b64,0x2fd6bbff,0xbb64b61f,0x3bf12648,0x361fbb64,0xb5053bce,0x3b64361f,0xbb99b303,
0x3a6d36d7,0xbbff3505,0xb8c43b3b,0xa648bb99,0xb81db9ed,0x3ac23444,0x3addb95f,0xb8483bb6,0x30b23b88,0xb67cba0f,0xbbea3564,0x3b50b93a,
0x33c6bbfe,0xb1793bf1,0x3bc32a48,0xbbe22fd6,0x3a2fbb0e,0xb3033bb6,0x3913378b,0xbbce3444,0xbbf634a5,0x3b77ba0f,0x2e46bba8,0x35c2393a,
0x3913378b,0xba8aafd6,0xba2f3b0e,0x389bbbf1,0x2e46bba8,0xa6483b25,0x3bf6b4a5,0xbbff3732,0xb6d7b81d,0x3b25b303,0x3b3bbadd,0xb7323bce,
0xb95f3bea,0x3444bb50,0xb9edb0b2,0x3bb6b67c,0x3b88b3c6,0xbbfa389b,0xb5643bc3,0x2cb5ba8a,0xaa48ba6d,0x2fd63984,0x3bfeb8c4,0xbbf139cb,
0xbbd93aa7,0x393abbe2,0xb23eb872,0x3a0fb179,0x323e3872,0xb8eca648,0xbbd93aa7,0x3a4fbbff,0x3bd9baa7,0xbb253bce,0x323e3872,0xb732b303,
0xb23eb872,0x3444367c,0x3bd9baa7,0xbbb63b50,0xaa4838c4,0xb89b2fd6,0xbbfe3a6d,0x3a8abbf1,0x3b3bb81d,0xbbff3b25,0xb6d73add,0xa648b732,
0x39edbbea,0xb8483af6,0x395fb0b2,0xbac237e3,0xb564b3c6,0x367c2cb5,0x3b88bbc3,0xbb503bfa,0x3ba8ba2f,0xbb773bfa,0xb4a53913,0xb5c22cb5,
0x3b0ebbf6,0xb89b3a4f,0x378bae46,0xba8a38ec,0x34a5b913,0xa6483505,0x3ba8ba2f,0xbbff3b99,0xb78b2e46,0x3848b444,0x3b0ebbf6,0xbac23bb6,
0x381db95f,0x2fd6a648,0x3addb9ed,0xbbf13bff,0x30b2b564,0x3505b303,0x3beabb88,0xbb993bce,0xb3c62a48,0x37e3b67c,0x3bc3bbfe,0xbaf63b50,
0xb8c436d7,0x393ab89b,0x3a6dbb3b,0xba0f3a8a,0xb9a839a8,0x3bf1bbff,0x39a8b9a8,0xafd62648,0xb9a839a8,0x3b99bbce,0x39a8b9a8,0xb5053303,
0xb9a839a8,0x3af6bb50,0x39a8b9a8,0xb7e3367c,0xb9a839a8,0x3a0fba8a,0x39a8b9a8,0xb93a389b,0xbadd39ed,0x35c2acb5,0xb81d395f,0x3b77bbfa,
0xbbea3b88,0x3a8ab8ec,0xb0b23564,0x389bba4f,0xbbc33bfe,0x3bffbb99,0x33c6aa48,0x2648b505,0xba6d3b3b,0x3ac2bbb6,0x38c4b6d7,0xb8483444,
0x34a5b913,0xba8a3bf1,0xbba83a2f,0x389bafd6,0xb78b2e46,0x26483732,0xbb0e3bf6,0x3bffbb25,0xbba83a2f,0x3ac2b7e3,0xb4a53913,0x3848baf6,
0xbb0e3bf6,0x3b50bbfa,0x378bae46,0xb67cacb5,0x3bfeba6d,0xba0f3179,0x2a48b8c4,0xb93a3be2,0x36d7badd,0xba4f3bff,0xbb3b381d,0x38ec2648,
0xb95f30b2,0x37323303,0xb9ed3bea,0x3b25bbce,0xbb883bc3,0x3bb6bb50,0x356433c6,0xb444b67c,0x323e3872,0x3732bbce,0x3bd9baa7,0xbb253303,
0x3bd9baa7,0xbbb6367c,0xb23eb872,0xb4443b50,0xb23eb872,0xacb53a8a,0xbbd93aa7,0x3bfab89b,0xbbd93aa7,0x3bf1b9cb,0x323e3872,0xafd6b984,
0xbb3b3add,0x3bceb444,0x36d7381d,0x3303bbb6,0x39ed30b2,0xb5c2b93a,0x395fbbea,0xbb773a0f,0x3564bbc3,0xb89b3bf1,0xbb8833c6,0x3a8a2fd6,
0xbbfe38c4,0x3bffb732,0x2a483a6d,0x2648bb25,0xb913b78b,0x26483b99,0xba2f3b0e,0x3bffb505,0xae463ba8,0x3848bbb6,0x3bf6b4a5,0xbac2b444,
0x3a2fbb0e,0xbb50393a,0xb913b78b,0x367c3a0f,0xbbf634a5,0x3be2afd6,0xae463ba8,0x3179bbf1,0x38c4bb3b,0xbbb635c2,0xba6db6d7,0x34443b77,
0xbadd395f,0x3bfab179,0x381d39ed,0xacb5bbe2,0x3beab564,0xbbf1a648,0xb0b2bb88,0xafd63bff,0xbbc3aa48,0x3b993303,0xb3c63bfe,0x3505bbce,
0x3b64361f,0xb7e3bb50,0x361fbb64,0xbaf6367c,0xbb64b61f,0x393a3a8a,0xb61f3b64,0x3a0fb89b,0x3b64361f,0xba4fb984,0x361fbb64,0xb8ec39cb,
0xbb64b61f,0x3b253848,0xb61f3b64,0x3732bac2,0xb0b23b88,0x39cbb732,0x3bea3564,0xb984bb25,0xb3c6bbfe,0xb3033af6,0xbbc32a48,0x3bce37e3,
0x38c43b3b,0xb5c2bbfa,0x3a6db6d7,0xbb772cb5,0xbaddb95f,0x3a8a3a4f,0xb81d39ed,0x389bb8ec,0xbbf6b4a5,0x3ac23af6,0x2e463ba8,0x3848b7e3,
0x3913b78b,0xbb50acb5,0xba2fbb0e,0x367c3bfa,0x2e463ba8,0x3179ba4f,0x3bf634a5,0xbbe2b8ec,0xba2fbb0e,0x39cb3b99,0xb913378b,0x3984b505,
0xb564bbc3,0xb5053848,0xbb88b3c6,0x3b993ac2,0x3bfe38c4,0xbaf6bb77,0x2a48ba6d,0xb7e335c2,0xb6d7381d,0x393ab179,0x3b3b3add,0xba0fbbe2,
0xb95fbbea,0x38ec3bff,0xb9ed30b2,0x3a4f2648,0x3aa7323e,0xbbfaba8a,0xb872bbd9,0xacb5389b,0x38723bd9,0xafd6b9cb,0x3aa7323e,0xbbf1b984,
0xbaa7b23e,0x3b993848,0x38723bd9,0xb505bac2,0xb872bbd9,0x37e33b77,0xbaa7b23e,0x3af635c2,0x39ed3bea,0xb179b8ec,0x395f30b2,0xbbe2ba4f,
0xb56433c6,0x39cb3505,0x3b883bc3,0xb984bb99,0xbbfeba6d,0x3bce3bb6,0x2a4838c4,0x3303b444,0xb6d7badd,0x35c23a0f,0xbb3bb81d,0x3b77393a,
0xb78bae46,0x3b503a0f,0x3b0e3bf6,0xb67cb93a,0xbba8ba2f,0x3be23bf1,0x34a53913,0x3179afd6,0xbb0ebbf6,0x39cb3b25,0xb78bae46,0x39843732,
0xb4a5b913,0x330337e3,0xbba8ba2f,0x3bce3af6,0xbbc3bbfe,0x38ec3984,0xb3c6aa48,0x3a4f39cb,0xba6dbb3b,0x37323848,0xb8c4b6d7,0x3b253ac2,
0xb81db95f,0x344435c2,0xbaddb9ed,0x3bb63b77,0xb0b2b564,0x2cb53179,0xbbeabb88,0x3bfa3be2,0x3c003c00,0x3a4f39cb,0,0x38ec3984,
0x3c003c00,0x3b253ac2,0,0x37323848,0x3c003c00,0x3bb63b77,0,0x344435c2,0x3c003c00,0x3bfa3be2,0,0x2cb53179,
0x33c62a48,0xb67cb93a,0x3bc33bfe,0x3b503a0f,0x38c436d7,0x3179afd6,0x3a6d3b3b,0x3be23bf1,0x3add39ed,0x39843732,0x381d395f,0x39cb3b25,
0x3bea3b88,0x3bce3af6,0x30b23564,0x330337e3,0xbb0ebbf6,0xbbe2ba4f,0x378b2e46,0xb179b8ec,0xb4a5b913,0xb984bb99,0x3ba83a2f,0x39cb3505,
0x378b2e46,0x3303b444,0x3b0e3bf6,0x3bce3bb6,0x3ba83a2f,0x3b77393a,0x34a53913,0x35c23a0f,0xb95fb0b2,0xacb5389b,0xb9edbbea,0xbbfaba8a,
0xbb88bbc3,0xbbf1b984,0x3564b3c6,0xafd6b9cb,0xaa48b8c4,0xb505bac2,0x3bfe3a6d,0x3b993848,0x3b3b381d,0x3af635c2,0x36d73add,0x37e33b77,
0x38723bd9,0x3b993ac2,0xbaa7b23e,0xb5053848,0xbaa7b23e,0xb7e335c2,0xb872bbd9,0xbaf6bb77,0xb872bbd9,0xba0fbbe2,0x3aa7323e,0x393ab179,
0x3aa7323e,0x3a4f2648,0x38723bd9,0x38ec3bff,0x3b8833c6,0x3848b7e3,0x35643bc3,0x3ac23af6,0xaa483a6d,0x367c3bfa,0xbbfeb8c4,0xbb50acb5,
0xbb3bbadd,0xbbe2b8ec,0x36d7b81d,0x3179ba4f,0x39edb0b2,0x3984b505,0x395f3bea,0x39cb3b99,0xae46bba8,0xb984bb25,0x3bf634a5,0x39cbb732,
0x3a2f3b0e,0x3bce37e3,0xb913378b,0xb3033af6,0xbbf6b4a5,0xbb772cb5,0xae46bba8,0xb5c2bbfa,0x3913b78b,0x389bb8ec,0x3a2f3b0e,0x3a8a3a4f,
0xbbeab564,0xbaf6367c,0x30b2bb88,0xb7e3bb50,0x3bc3aa48,0x3a0fb89b,0x33c63bfe,0x393a3a8a,0xba6d36d7,0xb8ec39cb,0xb8c4bb3b,0xba4fb984,
0x381db9ed,0x3732bac2,0x3add395f,0x3b253848,0xb61f3b64,0x34443b77,0xbb64b61f,0xbbb635c2,0x361fbb64,0xacb5bbe2,0x3b64361f,0x3bfab179,
0xb61f3b64,0xafd63bff,0xbb64b61f,0xbbf1a648,0x361fbb64,0x3505bbce,0x3b64361f,0x3b993303,0x3a6d36d7,0x3bffb505,0xb8c43b3b,0x26483b99,
0xb81db9ed,0xbac2b444,0x3addb95f,0x3848bbb6,0x30b23b88,0x367c3a0f,0xbbea3564,0xbb50393a,0x33c6bbfe,0x3179bbf1,0x3bc32a48,0x3be2afd6,
0x3a2fbb0e,0x3303bbb6,0x3913378b,0x3bceb444,0xbbf634a5,0xbb773a0f,0x2e46bba8,0xb5c2b93a,0x3913378b,0x3a8a2fd6,0xba2f3b0e,0xb89b3bf1,
0x2e46bba8,0x2648bb25,0x3bf6b4a5,0x3bffb732,0xb6d7b81d,0xbb253303,0x3b3bbadd,0x3732bbce,0xb95f3bea,0xb4443b50,0xb9edb0b2,0xbbb6367c,
0x3b88b3c6,0x3bfab89b,0xb5643bc3,0xacb53a8a,0xaa48ba6d,0xafd6b984,0x3bfeb8c4,0x3bf1b9cb,0xbbd93aa7,0xb93a3be2,0xb23eb872,0xba0f3179,
0x323e3872,0x38ec2648,0xbbd93aa7,0xba4f3bff,0x3bd9baa7,0x3b25bbce,0x323e3872,0x37323303,0xb23eb872,0xb444b67c,0x3bd9baa7,0x3bb6bb50,
0xaa4838c4,0x389bafd6,0xbbfe3a6d,0xba8a3bf1,0x3b3bb81d,0x3bffbb25,0xb6d73add,0x26483732,0x39edbbea,0x3848baf6,0x395fb0b2,0x3ac2b7e3,
0xb564b3c6,0xb67cacb5,0x3b88bbc3,0x3b50bbfa,0x3ba8ba2f,0x3b77bbfa,0xb4a53913,0x35c2acb5,0x3b0ebbf6,0x389bba4f,0x378bae46,0x3a8ab8ec,
0x34a5b913,0x2648b505,0x3ba8ba2f,0x3bffbb99,0xb78b2e46,0xb8483444,0x3b0ebbf6,0x3ac2bbb6,0x381db95f,0xafd62648,0x3addb9ed,0x3bf1bbff,
0x30b2b564,0xb5053303,0x3beabb88,0x3b99bbce,0xb3c62a48,0xb7e3367c,0x3bc3bbfe,0x3af6bb50,0xb8c436d7,0xb93a389b,0x3a6dbb3b,0x3a0fba8a,
0xb9a839a8,0xbbf13bff,0x39a8b9a8,0x2fd6a648,0xb9a839a8,0xbb993bce,0x39a8b9a8,0x3505b303,0xb9a839a8,0xbaf63b50,0x39a8b9a8,0x37e3b67c,
0xb9a839a8,0xba0f3a8a,0x39a8b9a8,0x393ab89b,0xbadd39ed,0xb5c22cb5,0xb81d395f,0xbb773bfa,0xbbea3b88,0xba8a38ec,0xb0b23564,0xb89b3a4f,
0xbbc33bfe,0xbbff3b99,0x33c6aa48,0xa6483505,0xba6d3b3b,0xbac23bb6,0x38c4b6d7,0x3848b444,0x34a5b913,0x3a8abbf1,0xbba83a2f,0xb89b2fd6,
0xb78b2e46,0xa648b732,0xbb0e3bf6,0xbbff3b25,0xbba83a2f,0xbac237e3,0xb4a53913,0xb8483af6,0xbb0e3bf6,0xbb503bfa,0x378bae46,0x367c2cb5,
0x3bfeba6d,0x3a0fb179,0x2a48b8c4,0x393abbe2,0x36d7badd,0x3a4fbbff,0xbb3b381d,0xb8eca648,0xb95f30b2,0xb732b303,0xb9ed3bea,0xbb253bce,
0xbb883bc3,0xbbb63b50,0x356433c6,0x3444367c,0x323e3872,0xb7323bce,0x3bd9baa7,0x3b25b303,0x3bd9baa7,0x3bb6b67c,0xb23eb872,0x3444bb50,
0xb23eb872,0x2cb5ba8a,0xbbd93aa7,0xbbfa389b,0xbbd93aa7,0xbbf139cb,0x323e3872,0x2fd63984,0xbb3b3add,0xbbce3444,0x36d7381d,0xb3033bb6,
0x39ed30b2,0x35c2393a,0x395fbbea,0x3b77ba0f,0x3564bbc3,0x389bbbf1,0xbb8833c6,0xba8aafd6,0xbbfe38c4,0xbbff3732,0x2a483a6d,0xa6483b25,
0xb913b78b,0xa648bb99,0xba2f3b0e,0xbbff3505,0xae463ba8,0xb8483bb6,0x3bf6b4a5,0x3ac23444,0x3a2fbb0e,0x3b50b93a,0xb913b78b,0xb67cba0f,
0xbbf634a5,0xbbe22fd6,0xae463ba8,0xb1793bf1,0x38c4bb3b,0x3bb6b5c2,0xba6db6d7,0xb444bb77,0xbadd395f,0xbbfa3179,0x381d39ed,0x2cb53be2,
0x3beab564,0x3bf12648,0xb0b2bb88,0x2fd6bbff,0xbbc3aa48,0xbb99b303,0xb3c63bfe,0xb5053bce,0x3b64361f,0x37e33b50,0x361fbb64,0x3af6b67c,
0xbb64b61f,0xb93aba8a,0xb61f3b64,0xba0f389b,0x3b64361f,0x3a4f3984,0x361fbb64,0x38ecb9cb,0xbb64b61f,0xbb25b848,0xb61f3b64,0xb7323ac2,
0xb0b23b88,0xb9cb3732,0x3bea3564,0x39843b25,0xb3c6bbfe,0x3303baf6,0xbbc32a48,0xbbceb7e3,0x38c43b3b,0x35c23bfa,0x3a6db6d7,0x3b77acb5,
0xbaddb95f,0xba8aba4f,0xb81d39ed,0xb89b38ec,0xbbf6b4a5,0xbac2baf6,0x2e463ba8,0xb84837e3,0x3913b78b,0x3b502cb5,0xba2fbb0e,0xb67cbbfa,
0x2e463ba8,0xb1793a4f,0x3bf634a5,0x3be238ec,0xba2fbb0e,0xb9cbbb99,0xb913378b,0xb9843505,0xb564bbc3,0x3505b848,0xbb88b3c6,0xbb99bac2,
0x3bfe38c4,0x3af63b77,0x2a48ba6d,0x37e3b5c2,0xb6d7381d,0xb93a3179,0x3b3b3add,0x3a0f3be2,0xb95fbbea,0xb8ecbbff,0xb9ed30b2,0xba4fa648,
0x3aa7323e,0x3bfa3a8a,0xb872bbd9,0x2cb5b89b,0x38723bd9,0x2fd639cb,0x3aa7323e,0x3bf13984,0xbaa7b23e,0xbb99b848,0x38723bd9,0x35053ac2,
0xb872bbd9,0xb7e3bb77,0xbaa7b23e,0xbaf6b5c2,0x39ed3bea,0x317938ec,0x395f30b2,0x3be23a4f,0xb56433c6,0xb9cbb505,0x3b883bc3,0x39843b99,
0xbbfeba6d,0xbbcebbb6,0x2a4838c4,0xb3033444,0xb6d7badd,0xb5c2ba0f,0xbb3bb81d,0xbb77b93a,0xb78bae46,0xbb50ba0f,0x3b0e3bf6,0x367c393a,
0xbba8ba2f,0xbbe2bbf1,0x34a53913,0xb1792fd6,0xbb0ebbf6,0xb9cbbb25,0xb78bae46,0xb984b732,0xb4a5b913,0xb303b7e3,0xbba8ba2f,0xbbcebaf6,
0xbbc3bbfe,0xb8ecb984,0xb3c6aa48,0xba4fb9cb,0xba6dbb3b,0xb732b848,0xb8c4b6d7,0xbb25bac2,0xb81db95f,0xb444b5c2,0xbaddb9ed,0xbbb6bb77,
0xb0b2b564,0xacb5b179,0xbbeabb88,0xbbfabbe2,0x3c003c00,0x96480000,0x3c003c00,0xa311a248,0x3c003c00,0x9cb69a48,0x3c003c00,0xa452a3db,
0x3c003c00,0x9fdb9e48,0x3c003c00,0xa51ba4b6,0x3c003c00,0xa17fa0b6,0x3bff3c00,0xa5e4a57f,0x3c003c00,0x9fdb0000,0x3bfb3bfc,0xac6aabd9,
0x3bff3c00,0xa5e4a3db,0x3bf93bfa,0xad65ace7,0x3bfe3bff,0xa8e8a7da,0x3bf63bf7,0xae5fade2,0x3bfd3bfe,0xaadea9e3,0x3bf23bf4,0xaf59aedc,
0x3c003c00,0xa3110000,0x3bf03bf4,0xafefaf0e,0x3bfe3bff,0xa94da711,0x3be83bed,0xb0d7b067,0x3bfb3bfd,0xac6aab11,0x3bdf3be4,0xb1b6b147,
0x3bf63bf9,0xae2dad4c,0x3bd43bda,0xb294b226,0x3c003c00,0xa51b0000,0x3bdf3be6,0xb1b6b115,0x3bfc3bfe,0xaba7a91b,0x3bcf3bd7,0xb2f7b257,
0x3bf63bf9,0xae5fad1a,0x3bbc3bc6,0xb41ab396,0x3bec3bf1,0xb074afa4,0x3ba53bb1,0xb4b7b469,0x3bff3c00,0xa6ad0000,0x3bc83bd4,0xb371b2a1,
0x3bfa3bfd,0xad00aaac,0x3bac3bbb,0xb487b420,0x3bef3bf5,0xb029aeaa,0x3b8b3b9d,0xb552b4ed,0x3bde3be7,0xb1cfb0fd,0x3b653b79,0xb61ab5b6,
0x3bff3c00,0xa81f0000,0x3bab3bbc,0xb493b414,0x3bf63bfc,0xae2dac1f,0x3b813b97,0xb58db511,0x3be53bef,0xb122b01d,0x3b4f3b69,0xb682b608,
0x3bcc3bda,0xb328b226,0x3b163b33,0xb76fb6f9,0x3bfe3c00,0xa8e80000,0x3b873ba0,0xb56ab4d5,0x3bf23bfa,0xaf59ace7,0x3b4c3b6b,0xb68db5fd,
0x3bda3be8,0xb219b0e4,0x3b073b2b,0xb7a6b71b,0x3bb73bca,0xb43eb34c,0x3ab63ae0,0xb85ab817,0x3bfe3c00,0xa9b10000,0x3b5e3b80,0xb63cb593,
0x3bee3bf8,0xb042adb0,0x3b103b39,0xb785b6e3,0x3bce3be0,0xb30fb1aa,0x3ab33ae3,0xb85fb812,0x3b9e3bb7,0xb4e7b438,0x3a493a7f,0xb8f3b8ab,
0x3bfd3c00,0xaa7a0000,0x3b2f3b5a,0xb70ab64e,0x3be83bf6,0xb0d7ae78,0x3acb3aff,0xb83ab7c2,0x3bbf3bd6,0xb402b26f,0x3a543a92,0xb8e5b891,
0x3b813ba2,0xb58db4c9,0x39cd3a13,0xb982b935,0x3bfd3c00,0xab430000,0x3afb3b30,0xb7d2b705,0x3be23bf3,0xb16caf40,0x3a7e3abf,0xb8adb84d,
0x3bae3bcb,0xb47bb334,0x39eb3a37,0xb962b909,0x3b603b8a,0xb631b558,0x3946399b,0xba04b9b5,0x3bfc3c00,0xac060000,0x3ac13b02,0xb84ab7b7,
0x3bdc3bf0,0xb201b004,0x3a293a78,0xb91bb8b5,0x3b9c3bc0,0xb4f3b3f7,0x397939d4,0xb9d6b97b,0x3b3d3b70,0xb6d2b5e5,0x38b23918,0xba7aba2b,
0x3bfb3c00,0xac6a0000,0x3a813ad0,0xb8a8b832,0x3bd43bed,0xb294b067,0x39cd3a2b,0xb982b918,0x3b873bb2,0xb56ab45d,0x38fd3969,0xba41b9e5,
0x3b163b53,0xb76fb670,0x3815388c,0xbae1ba95,0x3bfa3c00,0xacce0000,0x3a3d3a99,0xb902b887,0x3bcc3be9,0xb328b0cb,0x396b39d8,0xb9e3b976,
0x3b713ba4,0xb5dfb4bd,0x387a38f6,0xbaa2ba47,0x3aeb3b33,0xb805b6f9,0x36dd37ee,0xbb3abaf3,0x3bf93c00,0xad330000,0x39f43a5e,0xb958b8d8,
0x3bc33be5,0xb3bab12e,0x39023980,0xba3db9d0,0x3b593b95,0xb654b51d,0x37dd387c,0xbaf7baa0,0x3abd3b11,0xb850b780,0x358136b5,0xbb83bb43,
0x3bf83c00,0xad970000,0x39a63a1f,0xb9aab927,0x3bba3be1,0xb426b191,0x38943922,0xba90ba23,0x3b3f3b84,0xb6c6b57c,0x36bb37f9,0xbb42baf0,
0x3a8c3aed,0xb899b802,0x341a3570,0xbbbcbb86,0x3bf73c00,0xadfb0000,0x395439dc,0xb9f8b972,0x3bb03bdc,0xb46fb1f4,0x382038bf,0xbadbba71,
0x3b243b72,0xb737b5da,0x358d36ee,0xbb81bb36,0x3a583ac6,0xb8e0b842,0x31533420,0xbbe3bbbb,0x3bf63c00,0xae5f0000,0x38fd3996,0xba41b9ba,
0x3ba53bd7,0xb4b7b257,0x374e3858,0xbb1ebab8,0x3b073b5f,0xb7a6b637,0x345735da,0xbbb3bb72,0x3a213a9c,0xb924b881,0x2cce3191,0xbbfabbe1,
0x3bf53c00,0xaec30000,0x38a3394d,0xba85b9fe,0x3b9a3bd2,0xb4ffb2b9,0x365437d8,0xbb59baf9,0x3ae83b4b,0xb80ab693,0x323234bd,0xbbd9bba4,
0x39e73a71,0xb966b8bf,0xa4522db0,0xbc00bbf8,0x3bf33c00,0xaf270000,0x38453900,0xbac4ba3f,0x3b8e3bcd,0xb546b31b,0x355236f9,0xbb8bbb33,
0x3ac73b36,0xb840b6ee,0x2f593334,0xbbf2bbcb,0x39aa3a43,0xb9a6b8fb,0xaef51a48,0xbbf4bc00,0x3bf23c00,0xaf8b0000,0x37c838b0,0xbafeba7c,
0x3b813bc7,0xb58db37d,0x344b3614,0xbbb5bb67,0x3aa53b20,0xb874b748,0x288430e4,0xbbffbbe8,0x396b3a13,0xb9e3b935,0xb263ad4c,0xbbd7bbf9,
0x3bf03c00,0xafef0000,0x36ff385d,0xbb32bab5,0x3b733bc1,0xb5d4b3df,0x327c3529,0xbbd6bb93,0x3a813b08,0xb8a8b7a1,0xa9b12d1a,0xbbfebbf9,
0x392939e1,0xba1db96d,0xb49fb160,0xbba9bbe3,0x3bef3c00,0xb0290000,0x36313807,0xbb60bae9,0x3b653bbb,0xb61ab420,0x305b3438,0xbbedbbb7,
0x3a5c3af0,0xb8dbb7f9,0xafef1e48,0xbbf0bc00,0x38e539ad,0xba54b9a4,0xb602b408,0xbb6abbbe,0x3bed3c00,0xb05b0000,0x355e375e,0xbb89bb1a,
0x3b573bb4,0xb65fb451,0x2c6a3288,0xbbfbbbd5,0x3a353ad6,0xb90cb828,0xb27cac51,0xbbd6bbfb,0x389e3976,0xba89b9d8,0xb759b558,0xbb1bbb8a,
0x3beb3c00,0xb08d0000,0x348736aa,0xbbacbb46,0x3b473bad,0xb6a4b481,0x16483099,0xbc00bbeb,0x3a0d3abc,0xb93cb852,0xb47bb080,0xbbaebbec,
0x3855393e,0xbababa0b,0xb850b69e,0xbabdbb49,0x3be93c00,0xb0be0000,0x335935f1,0xbbc9bb6e,0x3b373ba6,0xb6e8b4b1,0xac382d4c,0xbbfcbbf9,
0x39e33aa0,0xb96bb87c,0xb5b1b2d2,0xbb7abbd1,0x380a3905,0xbae8ba3b,0xb8eab7d8,0xba50baf9,0x3be73c00,0xb0f00000,0x319e3534,0xbbe0bb91,
0x3b273b9e,0xb72cb4e1,0xb042257f,0xbbeebc00,0x39b83a83,0xb999b8a6,0xb6ddb48d,0xbb3abbab,0x377a38c9,0xbb13ba69,0xb979b881,0xb9d6ba9c,
0x3be53c00,0xb1220000,0x2fbd3475,0xbbf1bbaf,0x3b163b97,0xb76fb511,0xb263a91b,0xbbd7bbfe,0x398b3a65,0xb9c5b8ce,0xb7feb5ab,0xbaeebb7b,
0x36dd388c,0xbb3aba95,0xb9fcb90e,0xb94fba33,0x3be33c00,0xb1530000,0x2c383365,0xbbfcbbc9,0x3b043b8f,0xb7b2b540,0xb43eae78,0xbbb7bbf6,
0x395d3a47,0xb9f0b8f6,0xb889b6c1,0xba97bb41,0x363c384d,0xbb5ebabf,0xba73b992,0xb8bcb9be,0x3be13c00,0xb1850000,0x217f31db,0xbc00bbdd,
0x3af13b86,0xb7f3b570,0xb546b12e,0xbb8ebbe5,0x392e3a27,0xba19b91d,0xb90cb7cd,0xba35bafc,0x3599380d,0xbb7fbae6,0xbadbba0b,0xb820b93e,
0x3bdf3c00,0xb1b60000,0xa9b1304e,0xbbfebbed,0x3ade3b7d,0xb81ab59f,0xb648b31b,0xbb5cbbcd,0x38fd3a07,0xba41b943,0xb986b867,0xb9c9baae,
0x34f33796,0xbb9cbb0b,0xbb35ba78,0xb6f4b8b5,0x3bdd3c00,0xb1e80000,0xae5f2d7e,0xbbf6bbf8,0x3acb3b74,0xb83ab5ce,0xb742b481,0xbb21bbad,
0x38cc39e5,0xba67b969,0xb9f8b8e2,0xb954ba56,0x344b3710,0xbbb5bb2e,0xbb7fbad9,0xb599b822,0x3bda3c00,0xb2190000,0xb0f028b6,0xbbe7bbff,
0x3ab63b6b,0xb85ab5fd,0xb81ab570,0xbadebb86,0x389939c3,0xba8cb98d,0xba60b956,0xb8d6b9f6,0x33403687,0xbbcbbb4e,0xbbb8bb2e,0xb432b710,
0x3bff3bff,0xa6ada648,0x3bfe3bff,0xa8e8a8b6,0x3bff3bff,0xa776a711,0x3bfe3bfe,0xa94da91b,0x3bff3bff,0xa81fa7da,0x3bfe3bfe,0xa9b1a97f,
0x3bff3bff,0xa884a852,0x3bfe3bfe,0xaa16a9e3,0x3bef3bf1,0xb029afd6,0x3bda3bdd,0xb219b1db,0x3bea3bed,0xb0a6b067,0x3bd43bd7,0xb294b257,
0x3be53be8,0xb122b0e4,0x3bce3bd1,0xb30fb2d2,0x3be03be3,0xb19eb160,0x3bc63bca,0xb389b34c,0x3bc83bce,0xb371b303,0x3b873b91,0xb56ab534,
0x3bba3bc1,0xb426b3df,0x3b733b7d,0xb5d4b59f,0x3bab3bb2,0xb493b45d,0x3b5e3b69,0xb63cb608,0x3b9a3ba2,0xb4ffb4c9,0x3b473b53,0xb6a4b670,
0x3b8b3b99,0xb552b505,0x3b073b1a,0xb7a6b75e,0x3b6f3b7d,0xb5ebb59f,0x3ade3af3,0xb81ab7ee,0x3b4f3b5f,0xb682b637,0x3ab33ac9,0xb85fb83d,
0x3b2c3b3e,0xb715b6cc,0x3a853a9c,0xb8a3b881,0x3b3a3b50,0xb6ddb67c,0x3a5c3a7c,0xb8dbb8b0,0x3b0a3b22,0xb79bb73d,0x3a193a3b,0xb92eb905,
0x3ad53af0,0xb82ab7f9,0x39d239f6,0xb97db956,0x3a9b3ab8,0xb884b858,0x398639ad,0xb9c9b9a4,0x3ad53af6,0xb82ab7e3,0x398b39ba,0xb9c5b996,
0x3a8c3ab1,0xb899b862,0x3929395b,0xba1db9f2,0x3a3d3a65,0xb902b8ce,0x38c138f6,0xba6fba47,0x39e73a13,0xb966b935,0x3855388c,0xbababa95,
0x3a5c3a8a,0xb8dbb89b,0x389938d8,0xba8cba5e,0x39f83a2b,0xb954b918,0x38153858,0xbae1bab8,0x398b39c3,0xb9c5b98d,0x371537a1,0xbb2cbb08,
0x39163951,0xba2db9fa,0x35f73687,0xbb6cbb4e,0x39d23a0f,0xb97db93a,0x371537b7,0xbb2cbb02,0x394f3992,0xb9fcb9be,0x35c83670,0xbb76bb53,
0x38c13909,0xba6fba37,0x346f351d,0xbbb0bb95,0x382a3877,0xbad5baa3,0x3219337d,0xbbdabbc7,0x39373984,0xba11b9cb,0x34cf3593,0xbba1bb80,
0x389438e7,0xba90ba52,0x327c3408,0xbbd6bbbe,0x37c8383d,0xbafebac9,0x2e9130e4,0xbbf5bbe8,0x36543710,0xbb59bb2e,0x16482aac,0xbc00bbfd,
0x388e38ec,0xba93ba4f,0x30d732a1,0xbbe8bbd4,0x3790382d,0xbb0dbad3,0x28e82e14,0xbbfebbf7,0x35eb36c1,0xbb6fbb41,0xaccea4b6,0xbbfabc00,
0x34323511,0xbbb8bb97,0xb201b036,0xbbdcbbee,0x37b23848,0xbb04bac2,0x96482bd9,0xbc00bbfc,0x35df36cc,0xbb71bb3e,0xb010ac1f,0xbbefbbfc,
0x33eb34ed,0xbbc0bb9d,0xb402b20d,0xbbbfbbdb,0x2fef31f4,0xbbf0bbdc,0xb5ebb4f9,0xbb6fbb9b,0x36313732,0xbb60bb25,0xb0f0ad7e,0xbbe7bbf8,
0x341a3529,0xbbbcbb93,0xb49fb31b,0xbba9bbcd,0x2fbd320d,0xbbf1bbdb,0xb6afb5ab,0xbb45bb7b,0xa4522aac,0xbc00bbfd,0xb850b7ac,0xbabdbb05,
0x349f35c2,0xbba9bb77,0xb4dbb365,0xbb9fbbc9,0x308d32ea,0xbbebbbd0,0xb715b5fd,0xbb2cbb6b,0x9fdb2c51,0xbc00bbfb,0xb894b812,0xba90bae3,
0xb109ad4c,0xbbe6bbf9,0xb982b90e,0xb9cdba33,0x32013444,0xbbdcbbb6,0xb721b5f1,0xbb2abb6e,0x26ad2edc,0xbbffbbf4,0xb8adb822,0xba7ebad9,
0xb05bab11,0xbbedbbfd,0xb9aab930,0xb9a6ba17,0xb4b7b2ea,0xbba5bbd0,0xba81ba1b,0xb8a8b92b,0x2d653179,0xbbf9bbe2,0xb89eb807,0xba89bae9,
0xadc99a48,0xbbf8bc00,0xb9afb92b,0xb9a1ba1b,0xb432b1aa,0xbbb8bbe0,0xba93ba27,0xb88eb91d,0xb6d2b587,0xbb3dbb82,0xbb45baf3,0xb6afb7ee,
0xa51b2cb5,0xbc00bbfa,0xb990b900,0xb9c0ba3f,0xb294af40,0xbbd4bbf3,0xba89ba13,0xb89eb935,0xb625b4bd,0xbb63bba4,0xbb47baf0,0xb6a4b7f9,
0xb865b780,0xbab0bb11,0xbbc5bb8f,0xb3a2b540,0xafefa648,0xbbf0bbff,0xba60b9dc,0xb8d6b972,0xb517b31b,0xbb96bbcd,0xbb35bad3,0xb6f4b82d,
0xb7feb693,0xbaeebb4b,0xbbc0bb84,0xb3ebb57c,0xb94ab8ab,0xba00ba7f,0xbbfdbbe9,0xaa7ab0cb,0xb340afd6,0xbbcbbbf1,0xbb0aba99,0xb79bb887,
0xb6d2b540,0xbb3dbb8f,0xbbaebb67,0xb47bb614,0xb8dbb828,0xba5cbad6,0xbbfbbbe0,0xac9cb1aa,0xba15b980,0xb933b9d0,0xbbecbbff,0x30742852,
0xb53ab303,0xbb90bbce,0xbb89bb30,0xb55eb705,0xb83ab6e3,0xbacbbb39,0xbbf2bbca,0xaf8bb34c,0xb9a1b8f6,0xb9afba47,0xbbf5bc00,0x2ec39e48,
0xbac1ba3b,0xb84ab905,0xbb92bbd0,0x352f32ea,0xb6c6b505,0xbb3fbb99,0xbbdcbba0,0xb201b4d5,0xb8fdb838,0xba41bacc,0xbbfebbfb,0x2a16ac83,
0xba50b9b1,0xb8eab99f,0xbbaebbe4,0x347b3147,0xbb4abad9,0xb699b822,0xbaf1bb5d,0x37f33642,0xb820b67c,0xbadbbb50,0xbbffbbe6,0xa884b115,
0xb9afb8f1,0xb9a1ba4b,0xbbd2bbf8,0x32c62db0,0xbae5ba56,0xb80fb8e2,0xbb2abb8c,0x3721354c,0xbbaebb58,0xb47bb659,0xba11baaa,0x3937386d,
0xb8d1b7e3,0xba64baf6,0xbbf2bc00,0x2f8ba248,0xba4db99b,0xb8eeb9b5,0xbb6fbbc1,0x35eb33df,0xbb5cbae3,0xb648b812,0xba6bbafc,0x38c737cd,
0xbbebbbb4,0xb08db451,0xb8f8b9be,0x3a453992,0xb974b89b,0xb9daba8a,0xbbb5bbed,0x344b304e,0xbad5ba33,0xb82ab90e,0xbad8bb58,0x38253659,
0xbbb3bb55,0xb457b665,0xb979ba37,0x39d63909,0xbc00bbed,0x9648b067,0xb764b8a0,0x3b183a87,0xba09b93a,0xb941ba0f,0xbb4abbaf,0x36993475,
0xbb45bab8,0xb6afb858,0xba11babf,0x3937384d,0xbbeabbab,0xb0a6b48d,0xb85ab943,0x3ab63a07,0xbbecbc00,0x30749a48,0xb493b6b5,0x3bab3b43,
0xba8cb9cb,0xb899b984,0xbab3bb46,0x385f36aa,0xbb9cbb28,0xb4f3b726,0xb91fb9fa,0x3a253951,0xbc00bbe4,0xa452b147,0xb631b828,0x3b603ad6,
0xbbb0bbee,0x346f3036,0xae5fb3df,0x3bf63bc1,0xbafeba4f,0xb7c8b8ec,0xb9f4bab5,0x3958385d,0xbbd8bb82,0xb24bb587,0xb80ab90e,0x3ae83a33,
0xbbf3bbfe,0x2f27a97f,0xb2f7b5da,0x3bcf3b72,0xbb4cbbb7,0x368d3438,0x2dc9ac1f,0x3bf83bfc,0xbb5cbac2,0xb648b848,0xb911b9fe,0x3a31394d,
0xbbf9bbc4,0xad33b3ae,0xb5b1b802,0x3b7a3aed,0xbbc5bbf9,0x33a22d1a,0xa94db26f,0x3bfe3bd6,0xbac4bb5d,0x38453642,0x346f2fa4,0x3bb03bf1,
0xbba5bb25,0xb4b7b732,0xb80fb927,0x3ae53a1f,0xbbffbbee,0x2884b036,0xb24bb5b6,0x3bd83b79,0xbb76bbd6,0x35c8326f,0x305ba7da,0x3bed3bff,
0xba19bae0,0x392e3817,0x374234c9,0x3b213ba2,0xbbd9bb77,0xb232b5c2,0xb5ebb832,0x3b6f3ad0,0xbbe8bc00,0x30d7a57f,0xa81fb288,0x3bff3bd5,
0xbb07bb95,0x37a6351d,0x34f33080,0x3b9c3bec,0xb94fba43,0x39fc38fb,0x38ea3780,0x3a503b11,0xbbf8bbb6,0xadc9b444,0xb328b64e,0x3bcc3b5a,
0xbbb7bbf8,0x343e2db0,0x3042a9e3,0x3bee3bfe,0xba7abb36,0x38b236ee,0x379034ed,0x3b0d3b9d,0xb86ab989,0x3aac39c7,0x3a0438fb,0x39463a43,
0xbc00bbe2,0x2311b179,0xac9cb414,0x3bfb3bbc,0xbb6abbd7,0x36023257,0x34b72f40,0x3ba53bf3,0xb9d2babc,0x397d3852,0x38f83775,0x3a453b14,
0xb6ddb8b5,0x3b3a3a78,0x3ae83a0b,0x380a393e,0xbbf2bbfa,0x2f8bacb5,0x2d33af0e,0x3bf93bf4,0xbb04bb9e,0x37b234e1,0x372c3451,0x3b273bb4,
0xb911ba27,0x3a31391d,0x3a0038e2,0x394a3a56,0xb4c3b796,0x3ba33b0b,0x3b8b3ae6,0x3552380d,0x4c004c00,0x26480000,0x4c004c00,0x33113248,
0x4c004c00,0x2cb62a48,0x4c004c00,0x345233db,0x4c004c00,0x2fdb2e48,0x4c004c00,0x351b34b6,0x4c004c00,0x317f30b6,0x4bff4c00,0x35e4357f,
0x4c004c00,0x2fdb0000,0x4bfb4bfc,0x3c6a3bd9,0x4bff4c00,0x35e433db,0x4bf94bfa,0x3d653ce7,0x4bfe4bff,0x38e837da,0x4bf64bf7,0x3e5f3de2,
0x4bfd4bfe,0x3ade39e3,0x4bf24bf4,0x3f593edc,0x4c004c00,0x33110000,0x4bf04bf4,0x3fef3f0e,0x4bfe4bff,0x394d3711,0x4be84bed,0x40d74067,
0x4bfb4bfd,0x3c6a3b11,0x4bdf4be4,0x41b64147,0x4bf64bf9,0x3e2d3d4c,0x4bd44bda,0x42944226,0x4c004c00,0x351b0000,0x4bdf4be6,0x41b64115,
0x4bfc4bfe,0x3ba7391b,0x4bcf4bd7,0x42f74257,0x4bf64bf9,0x3e5f3d1a,0x4bbc4bc6,0x441a4396,0x4bec4bf1,0x40743fa4,0x4ba54bb1,0x44b74469,
0x4bff4c00,0x36ad0000,0x4bc84bd4,0x437142a1,0x4bfa4bfd,0x3d003aac,0x4bac4bbb,0x44874420,0x4bef4bf5,0x40293eaa,0x4b8b4b9d,0x455244ed,
0x4bde4be7,0x41cf40fd,0x4b654b79,0x461a45b6,0x4bff4c00,0x381f0000,0x4bab4bbc,0x44934414,0x4bf64bfc,0x3e2d3c1f,0x4b814b97,0x458d4511,
0x4be54bef,0x4122401d,0x4b4f4b69,0x46824608,0x4bcc4bda,0x43284226,0x4b164b33,0x476f46f9,0x4bfe4c00,0x38e80000,0x4b874ba0,0x456a44d5,
0x4bf24bfa,0x3f593ce7,0x4b4c4b6b,0x468d45fd,0x4bda4be8,0x421940e4,0x4b074b2b,0x47a6471b,0x4bb74bca,0x443e434c,0x4ab64ae0,0x485a4817,
0x4bfe4c00,0x39b10000,0x4b5e4b80,0x463c4593,0x4bee4bf8,0x40423db0,0x4b104b39,0x478546e3,0x4bce4be0,0x430f41aa,0x4ab34ae3,0x485f4812,
0x4b9e4bb7,0x44e74438,0x4a494a7f,0x48f348ab,0x4bfd4c00,0x3a7a0000,0x4b2f4b5a,0x470a464e,0x4be84bf6,0x40d73e78,0x4acb4aff,0x483a47c2,
0x4bbf4bd6,0x4402426f,0x4a544a92,0x48e54891,0x4b814ba2,0x458d44c9,0x49cd4a13,0x49824935,0x4bfd4c00,0x3b430000,0x4afb4b30,0x47d24705,
0x4be24bf3,0x416c3f40,0x4a7e4abf,0x48ad484d,0x4bae4bcb,0x447b4334,0x49eb4a37,0x49624909,0x4b604b8a,0x46314558,0x4946499b,0x4a0449b5,
0x4bfc4c00,0x3c060000,0x4ac14b02,0x484a47b7,0x4bdc4bf0,0x42014004,0x4a294a78,0x491b48b5,0x4b9c4bc0,0x44f343f7,0x497949d4,0x49d6497b,
0x4b3d4b70,0x46d245e5,0x48b24918,0x4a7a4a2b,0x4bfb4c00,0x3c6a0000,0x4a814ad0,0x48a84832,0x4bd44bed,0x42944067,0x49cd4a2b,0x49824918,
0x4b874bb2,0x456a445d,0x48fd4969,0x4a4149e5,0x4b164b53,0x476f4670,0x4815488c,0x4ae14a95,0x4bfa4c00,0x3cce0000,0x4a3d4a99,0x49024887,
0x4bcc4be9,0x432840cb,0x496b49d8,0x49e34976,0x4b714ba4,0x45df44bd,0x487a48f6,0x4aa24a47,0x4aeb4b33,0x480546f9,0x46dd47ee,0x4b3a4af3,
0x4bf94c00,0x3d330000,0x49f44a5e,0x495848d8,0x4bc34be5,0x43ba412e,0x49024980,0x4a3d49d0,0x4b594b95,0x4654451d,0x47dd487c,0x4af74aa0,
0x4abd4b11,0x48504780,0x458146b5,0x4b834b43,0x4bf84c00,0x3d970000,0x49a64a1f,0x49aa4927,0x4bba4be1,0x44264191,0x48944922,0x4a904a23,
0x4b3f4b84,0x46c6457c,0x46bb47f9,0x4b424af0,0x4a8c4aed,0x48994802,0x441a4570,0x4bbc4b86,0x4bf74c00,0x3dfb0000,0x495449dc,0x49f84972,
0x4bb04bdc,0x446f41f4,0x482048bf,0x4adb4a71,0x4b244b72,0x473745da,0x458d46ee,0x4b814b36,0x4a584ac6,0x48e04842,0x41534420,0x4be34bbb,
0x4bf64c00,0x3e5f0000,0x48fd4996,0x4a4149ba,0x4ba54bd7,0x44b74257,0x474e4858,0x4b1e4ab8,0x4b074b5f,0x47a64637,0x445745da,0x4bb34b72,
0x4a214a9c,0x49244881,0x3cce4191,0x4bfa4be1,0x4bf54c00,0x3ec30000,0x48a3494d,0x4a8549fe,0x4b9a4bd2,0x44ff42b9,0x465447d8,0x4b594af9,
0x4ae84b4b,0x480a4693,0x423244bd,0x4bd94ba4,0x49e74a71,0x496648bf,0xb4523db0,0x4c004bf8,0x4bf34c00,0x3f270000,0x48454900,0x4ac44a3f,
0x4b8e4bcd,0x4546431b,0x455246f9,0x4b8b4b33,0x4ac74b36,0x484046ee,0x3f594334,0x4bf24bcb,0x49aa4a43,0x49a648fb,0xbef52a48,0x4bf44c00,
0x4bf24c00,0x3f8b0000,0x47c848b0,0x4afe4a7c,0x4b814bc7,0x458d437d,0x444b4614,0x4bb54b67,0x4aa54b20,0x48744748,0x388440e4,0x4bff4be8,
0x496b4a13,0x49e34935,0xc263bd4c,0x4bd74bf9,0x4bf04c00,0x3fef0000,0x46ff485d,0x4b324ab5,0x4b734bc1,0x45d443df,0x427c4529,0x4bd64b93,
0x4a814b08,0x48a847a1,0xb9b13d1a,0x4bfe4bf9,0x492949e1,0x4a1d496d,0xc49fc160,0x4ba94be3,0x4bef4c00,0x40290000,0x46314807,0x4b604ae9,
0x4b654bbb,0x461a4420,0x405b4438,0x4bed4bb7,0x4a5c4af0,0x48db47f9,0xbfef2e48,0x4bf04c00,0x48e549ad,0x4a5449a4,0xc602c408,0x4b6a4bbe,
0x4bed4c00,0x405b0000,0x455e475e,0x4b894b1a,0x4b574bb4,0x465f4451,0x3c6a4288,0x4bfb4bd5,0x4a354ad6,0x490c4828,0xc27cbc51,0x4bd64bfb,
0x489e4976,0x4a8949d8,0xc759c558,0x4b1b4b8a,0x4beb4c00,0x408d0000,0x448746aa,0x4bac4b46,0x4b474bad,0x46a44481,0x26484099,0x4c004beb,
0x4a0d4abc,0x493c4852,0xc47bc080,0x4bae4bec,0x4855493e,0x4aba4a0b,0xc850c69e,0x4abd4b49,0x4be94c00,0x40be0000,0x435945f1,0x4bc94b6e,
0x4b374ba6,0x46e844b1,0xbc383d4c,0x4bfc4bf9,0x49e34aa0,0x496b487c,0xc5b1c2d2,0x4b7a4bd1,0x480a4905,0x4ae84a3b,0xc8eac7d8,0x4a504af9,
0x4be74c00,0x40f00000,0x419e4534,0x4be04b91,0x4b274b9e,0x472c44e1,0xc042357f,0x4bee4c00,0x49b84a83,0x499948a6,0xc6ddc48d,0x4b3a4bab,
0x477a48c9,0x4b134a69,0xc979c881,0x49d64a9c,0x4be54c00,0x41220000,0x3fbd4475,0x4bf14baf,0x4b164b97,0x476f4511,0xc263b91b,0x4bd74bfe,
0x498b4a65,0x49c548ce,0xc7fec5ab,0x4aee4b7b,0x46dd488c,0x4b3a4a95,0xc9fcc90e,0x494f4a33,0x4be34c00,0x41530000,0x3c384365,0x4bfc4bc9,
0x4b044b8f,0x47b24540,0xc43ebe78,0x4bb74bf6,0x495d4a47,0x49f048f6,0xc889c6c1,0x4a974b41,0x463c484d,0x4b5e4abf,0xca73c992,0x48bc49be,
0x4be14c00,0x41850000,0x317f41db,0x4c004bdd,0x4af14b86,0x47f34570,0xc546c12e,0x4b8e4be5,0x492e4a27,0x4a19491d,0xc90cc7cd,0x4a354afc,
0x4599480d,0x4b7f4ae6,0xcadbca0b,0x4820493e,0x4bdf4c00,0x41b60000,0xb9b1404e,0x4bfe4bed,0x4ade4b7d,0x481a459f,0xc648c31b,0x4b5c4bcd,
0x48fd4a07,0x4a414943,0xc986c867,0x49c94aae,0x44f34796,0x4b9c4b0b,0xcb35ca78,0x46f448b5,0x4bdd4c00,0x41e80000,0xbe5f3d7e,0x4bf64bf8,
0x4acb4b74,0x483a45ce,0xc742c481,0x4b214bad,0x48cc49e5,0x4a674969,0xc9f8c8e2,0x49544a56,0x444b4710,0x4bb54b2e,0xcb7fcad9,0x45994822,
0x4bda4c00,0x42190000,0xc0f038b6,0x4be74bff,0x4ab64b6b,0x485a45fd,0xc81ac570,0x4ade4b86,0x489949c3,0x4a8c498d,0xca60c956,0x48d649f6,
0x43404687,0x4bcb4b4e,0xcbb8cb2e,0x44324710,0x4bd84c00,0x424b0000,0xc2adb248,0x4bd34c00,0x4aa24b62,0x487a462b,0xc88ec659,0x4a934b58,
0x4865499f,0x4ab049b1,0xcabdc9c3,0x4850498d,0x41e845fd,0x4bdd4b6b,0xcbe1cb74,0x418545ce,0x4bd64c00,0x427c0000,0xc432bbd9,0x4bb84bfc,
0x4a8c4b58,0x48994659,0xc8fdc73d,0x4a414b22,0x4830497b,0x4ad149d4,0xcb10ca27,0x4785491d,0x408d4570,0x4beb4b86,0xcbf9cbad,0x3d334481,
0x4bd34c00,0x42ad0000,0xc50bbf0e,0x4b984bf4,0x4a764b4e,0x48b74687,0xc966c80d,0x49e74ae6,0x47f34956,0x4af149f6,0xcb57ca83,0x465f48a6,
0x3e5f44e1,0x4bf64b9e,0xcc00cbd7,0xb17f4257,0x4bd04c00,0x42de0000,0xc5dfc115,0x4b714be6,0x4a604b43,0x48d646b5,0xc9c9c877,0x49864aa3,
0x47854930,0x4b104a17,0xcb92cad6,0x452f4828,0x3b434451,0x4bfd4bb4,0xcbf5cbf3,0xbe913f40,0x4bce4c00,0x430f0000,0xc6afc2a1,0x4b454bd4,
0x4a494b39,0x48f346e3,0xca25c8dd,0x491f4a5a,0x47154909,0x4b2c4a37,0xcbc0cb20,0x43eb4748,0x3311437d,0x4c004bc7,0xcbd9cbff,0xc2323711,
0x4bcb4c00,0x43400000,0xc77ac414,0x4b134bbc,0x4a314b2e,0x49114710,0xca7ac93e,0x48b24a0b,0x46a448e2,0x4b474a56,0xcbe2cb5f,0x416c4637,
0xb7764257,0x4bff4bd7,0xcbaccbfd,0xc487bb75,0x4bc84c00,0x43710000,0xc820c4d5,0x4adb4ba0,0x4a194b22,0x492e473d,0xcac7c99b,0x484049b5,
0x463148ba,0x4b604a74,0xcbf8cb95,0x3dc9451d,0xbc9c412e,0x4bfb4be5,0xcb6fcbeb,0xc5ebc099,0x4bc54c00,0x43a20000,0xc87fc593,0x4a9e4b80,
0x4a004b17,0x494a476a,0xcb0dc9f2,0x4790495b,0x45bc4891,0x4b784a92,0xcc00cbc0,0x317f43f7,0xbf594004,0x4bf24bf0,0xcb21cbca,0xc742c34c,
0x4bc24c00,0x43d30000,0xc8dbc64e,0x4a5c4b5a,0x49e74b0b,0x49664796,0xcb4aca43,0x469948fb,0x45464867,0x4b8e4aae,0xcbfbcbe0,0xbc6a41aa,
0xc1093db0,0x4be64bf8,0xcac4cb9b,0xc845c4f9,0x4bbf4c00,0x44020000,0xc933c705,0x4a154b30,0x49cd4aff,0x498247c2,0xcb7fca8e,0x45994896,
0x44cf483d,0x4ba14ac9,0xcbe9cbf5,0xc0be3eaa,0xc2633aac,0x4bd74bfd,0xca58cb5d,0xc8e0c642,0x4bbc4c00,0x441a0000,0xc986c7b7,0x49c94b02,
0x49b34af3,0x499d47ee,0xcbabcad3,0x4493482d,0x44574812,0x4bb34ae3,0xcbcbcbff,0xc34037da,0xc3ba33db,0x4bc34c00,0xc9dfcb11,0xc970c780,
0x4bb84c00,0x44320000,0xc9d6c832,0x49794ad0,0x49994ae6,0x49b8480d,0xcbcecb11,0x430f4780,0x43ba47cd,0x4bc34afc,0xcb9fcbfe,0xc4dbb97f,
0xc487b57f,0x4bac4c00,0xc958cab8,0xc9f4c858,0x4bb54c00,0x444b0000,0xca21c887,0x49244a99,0x497d4ad9,0x49d24822,0xcbe7cb49,0x40f0469e,
0x42c64775,0x4bd24b14,0xcb68cbf2,0xc60ebf72,0xc52fbb75,0x4b924bfd,0xc8c7ca52,0xca6bc8e7,0x4bb24c00,0x44630000,0xca67c8d8,0x48cc4a5e,
0x49624acc,0x49eb4838,0xcbf8cb79,0x3d9745b6,0x41cf471b,0x4bde4b2b,0xcb24cbdb,0xc737c20d,0xc5d4be14,0x4b734bf7,0xc82ac9e1,0xcad5c96d,
0x4bae4c00,0x447b0000,0xcaa9c927,0x486f4a1f,0x49464abf,0x4a04484d,0xcc00cba2,0x351b44c9,0x40d746c1,0x4be84b41,0xcad5cbb9,0xc82ac42c,
0xc676c036,0x4b524bee,0xc70ac964,0xcb2fc9e9,0x4bab4c00,0x44930000,0xcae5c972,0x480f49dc,0x49294ab1,0x4a1d4862,0xcbfecbc4,0xba1643ae,
0x3fbd4665,0x4bf14b55,0xca7acb8c,0xc8b2c54c,0xc715c160,0x4b2c4be3,0xc5b1c8dd,0xcb7aca5a,0x4ba74c00,0x44ab0000,0xcb1bc9ba,0x47594996,
0x490c4aa3,0x4a354877,0xcbf2cbdf,0xbf5941c3,0x3dc94608,0x4bf84b69,0xca15cb55,0xc933c665,0xc7b2c288,0x4b044bd5,0xc44bc84d,0xcbb5cabf,
0x4ba34c00,0x44c30000,0xcb4cc9fe,0x468d494d,0x48ee4a95,0x4a4d488c,0xcbdecbf1,0xc1cf3fa4,0x3ba745ab,0x4bfc4b7b,0xc9a6cb14,0xc9aac775,
0xc825c3ae,0x4ad84bc4,0xc1b6c76a,0xcbdfcb17,0x4b9f4c00,0x44db0000,0xcb78ca3f,0x45bc4900,0x48d14a87,0x4a6448a0,0xcbc0cbfd,0xc3eb3b75,
0x3776454c,0x4bff4b8c,0xc92ecac9,0xca19c83d,0xc86fc469,0x4aa94bb1,0xbd97c62b,0xcbf8cb62,0x4b9c4c00,0x44f30000,0xcb9eca7c,0x44e748b0,
0x48b24a78,0x4a7a48b5,0xcb9acc00,0xc4ffaa48,0xa64844ed,0x4c004b9d,0xc8adca74,0xca7ec8ba,0xc8b7c4f9,0x4a764b9b,0x2cb6c4e1,0xcc00cb9e,
0x4b984c00,0x450b0000,0xcbbdcab5,0x440e485d,0x48944a69,0x4a9048c9,0xcb6acbfc,0xc602bc1f,0xb81f448d,0x4bff4bab,0xc825ca17,0xcad8c930,
0xc8fdc587,0x4a414b82,0x3e2dc31b,0xcbf6cbcd,0x4b944c00,0x45230000,0xcbd7cae9,0x42634807,0x48744a5a,0x4aa548dd,0xcb32cbf0,0xc6ffc004,
0xbc06442c,0x4bfc4bb9,0xc72cc9b1,0xcb27c99f,0xc941c614,0x4a094b67,0x4201c067,0xcbdccbed,0x4b904c00,0x453a0000,0xcbeacb1a,0x40a6475e,
0x48554a4b,0x4aba48f1,0xcaf1cbdc,0xc7f3c1f4,0xbdfb4396,0x4bf74bc6,0xc602c943,0xcb6aca07,0xc982c69e,0x49cd4b49,0x446fbaac,0xcbb0cbfd,
0x4b8b4c00,0x45520000,0xcbf8cb46,0x3dc946aa,0x48354a3b,0x4ace4905,0xcaa9cbc1,0xc86fc3df,0xbfef42d2,0x4bf04bd1,0xc4cfc8ce,0xcba1ca65,
0xc9c0c726,0x49904b28,0x45d43852,0xcb73cbff,0x4b874c00,0x456a0000,0xcbffcb6e,0x388445f1,0x48154a2b,0x4ae14918,0xca58cb9e,0xc8e0c4e1,
0xc0f0420d,0x4be74bdb,0xc328c852,0xcbcccabc,0xc9fcc7ac,0x494f4b05,0x472c3fa4,0xcb27cbf1,0x4b834c00,0x45810000,0xcc00cb91,0xb51b4534,
0x47e84a1b,0x4af4492b,0xca00cb74,0xc94ac5ce,0xc1e84147,0x4bdd4be4,0xc0a6c7a1,0xcbeacb08,0xca35c817,0x490c4ae0,0x483a4288,0xcacbcbd5,
0x4b7f4c00,0x45990000,0xcbfacbaf,0xbcce4475,0x47a64a0b,0x4b07493e,0xc9a1cb43,0xc9afc6b5,0xc2de4080,0x4bd04bec,0xbc38c693,0xcbfccb4b,
0xca6bc858,0x48c74ab8,0x48d64499,0xca60cbaa,0x4b7a4c00,0x45b10000,0xcbefcbc9,0xc0294365,0x476449fa,0x4b184951,0xc93ccb0b,0xca0dc796,
0xc3d33f72,0x4bc24bf2,0x3311c57c,0xcc00cb84,0xca9ec896,0x487f4a8e,0x496645e5,0xc9e7cb70,0x4b764c00,0x45c80000,0xcbddcbdd,0xc1e841db,
0x472149e9,0x4b2a4964,0xc8d1cacc,0xca64c838,0xc4633de2,0x4bb24bf7,0x3dfbc45d,0xcbf7cbb2,0xcacec8d3,0x48354a62,0x49eb4726,0xc962cb28,
0x4b714c00,0x45df0000,0xcbc5cbed,0xc3a2404e,0x46dd49d8,0x4b3a4976,0xc85fca87,0xcab3c8a0,0xc4db3c51,0x4b9f4bfb,0x4185c26f,0xcbe1cbd6,
0xcafbc90e,0x47d24a33,0x4a64482d,0xc8d1cad3,0x4b6c4c00,0x45f70000,0xcba7cbf8,0xc4ab3d7e,0x469949c7,0x4b4a4989,0xc7d2ca3b,0xcafbc905,
0xc552397f,0x4b8b4bfe,0x4402c01d,0xcbbfcbef,0xcb24c948,0x47374a02,0x4ace48bf,0xc835ca71,0x4b684c00,0x460e0000,0xcb83cbff,0xc58138b6,
0x465449b5,0x4b59499b,0xc6ddc9e9,0xcb3ac964,0xc5c834b6,0x4b764c00,0x453abb11,0xcb90cbfd,0xcb4ac980,0x469949d0,0x4b2a4948,0xc721ca02,
0x2c002c00,0x2c002c00,0x2c002c00,0x2c002c00,0x2b642c00,0x261f29a8,0xa61f0000,0xab64a9a8,0x29a82c00,0xa9a80000,0xa9a8ac00,0x29a80000,
0x261f2c00,0xab64a9a8,0x2b640000,0xa61f29a8,0x2c00,0xac00,0x2c00,0xac00,0xa61f2c00,0x2b64a9a8,0xab640000,0x261f29a8,
0xa9a82c00,0x29a80000,0x29a8ac00,0xa9a80000,0xab642c00,0xa61f29a8,0x261f0000,0x2b64a9a8,0,0,0,0,
0x261f0000,0x2b6429a8,0x2b642c00,0x261f29a8,0x29a80000,0x29a82c00,0xa9a80000,0xa9a8ac00,0x2b640000,0xa61f29a8,0xa61fac00,0x2b6429a8,
0x2c000000,0xac000000,0x2c000000,0xac000000,0x2b640000,0xa61fa9a8,0xa61f2c00,0x2b64a9a8,0x29a80000,0x29a8ac00,0xa9a80000,0xa9a82c00,
0x261f0000,0x2b64a9a8,0x2b64ac00,0x261fa9a8,0xac002c00,0xac002c00,0xac002c00,0xac002c00,0xab642c00,0xa61f29a8,0x261f0000,0x2b64a9a8,
0xa9a82c00,0x29a80000,0x29a8ac00,0xa9a80000,0xa61f2c00,0x2b64a9a8,0xab640000,0x261f29a8,0x2c00,0xac00,0x2c00,0xac00,
0x261f2c00,0xab64a9a8,0x2b640000,0xa61f29a8,0x29a82c00,0xa9a80000,0xa9a8ac00,0x29a80000,0x2b642c00,0x261f29a8,0xa61f0000,0xab64a9a8,
0,0,0,0,0xa61f0000,0xab6429a8,0xab642c00,0xa61f29a8,0xa9a80000,0xa9a82c00,0x29a80000,0x29a8ac00,
0xab640000,0x261f29a8,0x261fac00,0xab6429a8,0xac000000,0x2c000000,0xac000000,0x2c000000,0xab640000,0x261fa9a8,0x261f2c00,0xab64a9a8,
0xa9a80000,0xa9a8ac00,0x29a80000,0x29a82c00,0xa61f0000,0xab64a9a8,0xab64ac00,0xa61fa9a8,0,0,0,0,
0xa61f0000,0xab64a9a8,0xab64ac00,0xa61fa9a8,0xa9a80000,0xa9a8ac00,0x29a80000,0x29a82c00,0xab640000,0x261fa9a8,0x261f2c00,0xab64a9a8,
0xac000000,0x2c000000,0xac000000,0x2c000000,0xab640000,0x261f29a8,0x261fac00,0xab6429a8,0xa9a80000,0xa9a82c00,0x29a80000,0x29a8ac00,
0xa61f0000,0xab6429a8,0xab642c00,0xa61f29a8,0x2c002c00,0x2c002c00,0x2c002c00,0x2c002c00,0x2b642c00,0x261f29a8,0xa61f0000,0xab64a9a8,
0x29a82c00,0xa9a80000,0xa9a8ac00,0x29a80000,0x261f2c00,0xab64a9a8,0x2b640000,0xa61f29a8,0x2c00,0xac00,0x2c00,0xac00,
0xa61f2c00,0x2b64a9a8,0xab640000,0x261f29a8,0xa9a82c00,0x29a80000,0x29a8ac00,0xa9a80000,0xab642c00,0xa61f29a8,0x261f0000,0x2b64a9a8,
0,0,0,0,0x261f0000,0x2b64a9a8,0x2b64ac00,0x261fa9a8,0x29a80000,0x29a8ac00,0xa9a80000,0xa9a82c00,
0x2b640000,0xa61fa9a8,0xa61f2c00,0x2b64a9a8,0x2c000000,0xac000000,0x2c000000,0xac000000,0x2b640000,0xa61f29a8,0xa61fac00,0x2b6429a8,
0x29a80000,0x29a82c00,0xa9a80000,0xa9a8ac00,0x261f0000,0x2b6429a8,0x2b642c00,0x261f29a8,0xac002c00,0xac002c00,0xac002c00,0xac002c00,
0xab642c00,0xa61f29a8,0x261f0000,0x2b64a9a8,0xa9a82c00,0x29a80000,0x29a8ac00,0xa9a80000,0xa61f2c00,0x2b64a9a8,0xab640000,0x261f29a8,
0x2c00,0xac00,0x2c00,0xac00,0x261f2c00,0xab64a9a8,0x2b640000,0xa61f29a8,0x29a82c00,0xa9a80000,0xa9a8ac00,0x29a80000,
0x2b642c00,0x261f29a8,0xa61f0000,0xab64a9a8,0x2c002c00,0x2c002c00,0x2c002c00,0x2c002c00,0xab64ac00,0xa61fa9a8,0x261f0000,0x2b6429a8,
0x29a82c00,0xa9a80000,0xa9a8ac00,0x29a80000,0xa61fac00,0x2b6429a8,0xab640000,0x261fa9a8,0x2c00,0xac00,0x2c00,0xac00,
0x261fac00,0xab6429a8,0x2b640000,0xa61fa9a8,0xa9a82c00,0x29a80000,0x29a8ac00,0xa9a80000,0x2b64ac00,0x261fa9a8,0xa61f0000,0xab6429a8,
0,0,0,0,0xa61f0000,0xab64a9a8,0xab64ac00,0xa61fa9a8,0x29a80000,0x29a82c00,0xa9a80000,0xa9a8ac00,
0xab640000,0x261fa9a8,0x261f2c00,0xab64a9a8,0x2c000000,0xac000000,0x2c000000,0xac000000,0xab640000,0x261f29a8,0x261fac00,0xab6429a8,
0x29a80000,0x29a8ac00,0xa9a80000,0xa9a82c00,0xa61f0000,0xab6429a8,0xab642c00,0xa61f29a8,0xac002c00,0xac002c00,0xac002c00,0xac002c00,
0x2b64ac00,0x261fa9a8,0xa61f0000,0xab6429a8,0xa9a82c00,0x29a80000,0x29a8ac00,0xa9a80000,0x261fac00,0xab6429a8,0x2b640000,0xa61fa9a8,
0x2c00,0xac00,0x2c00,0xac00,0xa61fac00,0x2b6429a8,0xab640000,0x261fa9a8,0x29a82c00,0xa9a80000,0xa9a8ac00,0x29a80000,
0xab64ac00,0xa61fa9a8,0x261f0000,0x2b6429a8,0,0,0,0,0x261f0000,0x2b64a9a8,0x2b64ac00,0x261fa9a8,
0xa9a80000,0xa9a82c00,0x29a80000,0x29a8ac00,0x2b640000,0xa61fa9a8,0xa61f2c00,0x2b64a9a8,0xac000000,0x2c000000,0xac000000,0x2c000000,
0x2b640000,0xa61f29a8,0xa61fac00,0x2b6429a8,0xa9a80000,0xa9a8ac00,0x29a80000,0x29a82c00,0x261f0000,0x2b6429a8,0x2b642c00,0x261f29a8,
0,0,0,0,0x261f0000,0x2b6429a8,0x2b642c00,0x261f29a8,0xa9a80000,0xa9a8ac00,0x29a80000,0x29a82c00,
0x2b640000,0xa61f29a8,0xa61fac00,0x2b6429a8,0xac000000,0x2c000000,0xac000000,0x2c000000,0x2b640000,0xa61fa9a8,0xa61f2c00,0x2b64a9a8,
0xa9a80000,0xa9a82c00,0x29a80000,0x29a8ac00,0x261f0000,0x2b64a9a8,0x2b64ac00,0x261fa9a8,0x2c002c00,0x2c002c00,0x2c002c00,0x2c002c00,
0xab64ac00,0xa61fa9a8,0x261f0000,0x2b6429a8,0x29a82c00,0xa9a80000,0xa9a8ac00,0x29a80000,0xa61fac00,0x2b6429a8,0xab640000,0x261fa9a8,
0x2c00,0xac00,0x2c00,0xac00,0x261fac00,0xab6429a8,0x2b640000,0xa61fa9a8,0xa9a82c00,0x29a80000,0x29a8ac00,0xa9a80000,
0x2b64ac00,0x261fa9a8,0xa61f0000,0xab6429a8,0,0,0,0,0xa61f0000,0xab6429a8,0xab642c00,0xa61f29a8,
0x29a80000,0x29a8ac00,0xa9a80000,0xa9a82c00,0xab640000,0x261f29a8,0x261fac00,0xab6429a8,0x2c000000,0xac000000,0x2c000000,0xac000000,
0xab640000,0x261fa9a8,0x261f2c00,0xab64a9a8,0x29a80000,0x29a82c00,0xa9a80000,0xa9a8ac00,0xa61f0000,0xab64a9a8,0xab64ac00,0xa61fa9a8,
0xac002c00,0xac002c00,0xac002c00,0xac002c00,0x2b64ac00,0x261fa9a8,0xa61f0000,0xab6429a8,0xa9a82c00,0x29a80000,0x29a8ac00,0xa9a80000,
0x261fac00,0xab6429a8,0x2b640000,0xa61fa9a8,0x2c00,0xac00,0x2c00,0xac00,0xa61fac00,0x2b6429a8,0xab640000,0x261fa9a8,
0x29a82c00,0xa9a80000,0xa9a8ac00,0x29a80000,0xab64ac00,0xa61fa9a8,0x261f0000,0x2b6429a8,0x2bd92c00,0x2aa72b64,0x287229a8,0x223e261f,
0x2aa72c00,0xa23e261f,0xabd9a9a8,0xa872ab64,0x28722c00,0xabd9a61f,0x223ea9a8,0x2aa72b64,0x223e2c00,0xa872ab64,0x2aa729a8,0xabd9a61f,
0xa23e2c00,0x2872ab64,0xaaa729a8,0x2bd9a61f,0xa8722c00,0x2bd9a61f,0xa23ea9a8,0xaaa72b64,0xaaa72c00,0x223e261f,0x2bd9a9a8,0x2872ab64,
0xabd92c00,0xaaa72b64,0xa87229a8,0xa23e261f,0x223e0000,0x2872261f,0x2aa729a8,0x2bd92b64,0x28720000,0x2bd92b64,0x223e29a8,0xaaa7a61f,
0x2aa70000,0x223e2b64,0xabd9a9a8,0x2872a61f,0x2bd90000,0xaaa7261f,0x2872a9a8,0xa23e2b64,0x2bd90000,0xaaa7a61f,0x287229a8,0xa23eab64,
0x2aa70000,0x223eab64,0xabd929a8,0x2872261f,0x28720000,0x2bd9ab64,0x223ea9a8,0xaaa7261f,0x223e0000,0x2872a61f,0x2aa7a9a8,0x2bd9ab64,
0xabd92c00,0xaaa72b64,0xa87229a8,0xa23e261f,0xaaa72c00,0x223e261f,0x2bd9a9a8,0x2872ab64,0xa8722c00,0x2bd9a61f,0xa23ea9a8,0xaaa72b64,
0xa23e2c00,0x2872ab64,0xaaa729a8,0x2bd9a61f,0x223e2c00,0xa872ab64,0x2aa729a8,0xabd9a61f,0x28722c00,0xabd9a61f,0x223ea9a8,0x2aa72b64,
0x2aa72c00,0xa23e261f,0xabd9a9a8,0xa872ab64,0x2bd92c00,0x2aa72b64,0x287229a8,0x223e261f,0xa23e0000,0xa872261f,0xaaa729a8,0xabd92b64,
0xa8720000,0xabd92b64,0xa23e29a8,0x2aa7a61f,0xaaa70000,0xa23e2b64,0x2bd9a9a8,0xa872a61f,0xabd90000,0x2aa7261f,0xa872a9a8,0x223e2b64,
0xabd90000,0x2aa7a61f,0xa87229a8,0x223eab64,0xaaa70000,0xa23eab64,0x2bd929a8,0xa872261f,0xa8720000,0xabd9ab64,0xa23ea9a8,0x2aa7261f,
0xa23e0000,0xa872a61f,0xaaa7a9a8,0xabd9ab64,0xa23e0000,0xa872a61f,0xaaa7a9a8,0xabd9ab64,0xa8720000,0xabd9ab64,0xa23ea9a8,0x2aa7261f,
0xaaa70000,0xa23eab64,0x2bd929a8,0xa872261f,0xabd90000,0x2aa7a61f,0xa87229a8,0x223eab64,0xabd90000,0x2aa7261f,0xa872a9a8,0x223e2b64,
0xaaa70000,0xa23e2b64,0x2bd9a9a8,0xa872a61f,0xa8720000,0xabd92b64,0xa23e29a8,0x2aa7a61f,0xa23e0000,0xa872261f,0xaaa729a8,0xabd92b64,
0x2bd92c00,0x2aa72b64,0x287229a8,0x223e261f,0x2aa72c00,0xa23e261f,0xabd9a9a8,0xa872ab64,0x28722c00,0xabd9a61f,0x223ea9a8,0x2aa72b64,
0x223e2c00,0xa872ab64,0x2aa729a8,0xabd9a61f,0xa23e2c00,0x2872ab64,0xaaa729a8,0x2bd9a61f,0xa8722c00,0x2bd9a61f,0xa23ea9a8,0xaaa72b64,
0xaaa72c00,0x223e261f,0x2bd9a9a8,0x2872ab64,0xabd92c00,0xaaa72b64,0xa87229a8,0xa23e261f,0x223e0000,0x2872a61f,0x2aa7a9a8,0x2bd9ab64,
0x28720000,0x2bd9ab64,0x223ea9a8,0xaaa7261f,0x2aa70000,0x223eab64,0xabd929a8,0x2872261f,0x2bd90000,0xaaa7a61f,0x287229a8,0xa23eab64,
0x2bd90000,0xaaa7261f,0x2872a9a8,0xa23e2b64,0x2aa70000,0x223e2b64,0xabd9a9a8,0x2872a61f,0x28720000,0x2bd92b64,0x223e29a8,0xaaa7a61f,
0x223e0000,0x2872261f,0x2aa729a8,0x2bd92b64,0xabd92c00,0xaaa72b64,0xa87229a8,0xa23e261f,0xaaa72c00,0x223e261f,0x2bd9a9a8,0x2872ab64,
0xa8722c00,0x2bd9a61f,0xa23ea9a8,0xaaa72b64,0xa23e2c00,0x2872ab64,0xaaa729a8,0x2bd9a61f,0x223e2c00,0xa872ab64,0x2aa729a8,0xabd9a61f,
0x28722c00,0xabd9a61f,0x223ea9a8,0x2aa72b64,0x2aa72c00,0xa23e261f,0xabd9a9a8,0xa872ab64,0x2bd92c00,0x2aa72b64,0x287229a8,0x223e261f,
0xa23e0000,0xa872a61f,0xaaa7a9a8,0xabd9ab64,0x28720000,0x2bd92b64,0x223e29a8,0xaaa7a61f,0xaaa70000,0xa23eab64,0x2bd929a8,0xa872261f,
0x2bd90000,0xaaa7261f,0x2872a9a8,0xa23e2b64,0xabd90000,0x2aa7261f,0xa872a9a8,0x223e2b64,0x2aa70000,0x223eab64,0xabd929a8,0x2872261f,
0xa8720000,0xabd92b64,0xa23e29a8,0x2aa7a61f,0x223e0000,0x2872a61f,0x2aa7a9a8,0x2bd9ab64,0x2bd92c00,0x2aa72b64,0x287229a8,0x223e261f,
0xaaa7ac00,0x223ea61f,0x2bd929a8,0x28722b64,0x28722c00,0xabd9a61f,0x223ea9a8,0x2aa72b64,0xa23eac00,0x28722b64,0xaaa7a9a8,0x2bd9261f,
0xa23e2c00,0x2872ab64,0xaaa729a8,0x2bd9a61f,0x2872ac00,0xabd9261f,0x223e29a8,0x2aa7ab64,0xaaa72c00,0x223e261f,0x2bd9a9a8,0x2872ab64,
0x2bd9ac00,0x2aa7ab64,0x2872a9a8,0x223ea61f,0x223e0000,0x2872a61f,0x2aa7a9a8,0x2bd9ab64,0xa8720000,0xabd92b64,0xa23e29a8,0x2aa7a61f,
0x2aa70000,0x223eab64,0xabd929a8,0x2872261f,0xabd90000,0x2aa7261f,0xa872a9a8,0x223e2b64,0x2bd90000,0xaaa7261f,0x2872a9a8,0xa23e2b64,
0xaaa70000,0xa23eab64,0x2bd929a8,0xa872261f,0x28720000,0x2bd92b64,0x223e29a8,0xaaa7a61f,0xa23e0000,0xa872a61f,0xaaa7a9a8,0xabd9ab64,
0xabd92c00,0xaaa72b64,0xa87229a8,0xa23e261f,0x2aa7ac00,0xa23ea61f,0xabd929a8,0xa8722b64,0xa8722c00,0x2bd9a61f,0xa23ea9a8,0xaaa72b64,
0x223eac00,0xa8722b64,0x2aa7a9a8,0xabd9261f,0x223e2c00,0xa872ab64,0x2aa729a8,0xabd9a61f,0xa872ac00,0x2bd9261f,0xa23e29a8,0xaaa7ab64,
0x2aa72c00,0xa23e261f,0xabd9a9a8,0xa872ab64,0xabd9ac00,0xaaa7ab64,0xa872a9a8,0xa23ea61f,0xabd9ac00,0xaaa7ab64,0xa872a9a8,0xa23ea61f,
0x2aa72c00,0xa23e261f,0xabd9a9a8,0xa872ab64,0xa872ac00,0x2bd9261f,0xa23e29a8,0xaaa7ab64,0x223e2c00,0xa872ab64,0x2aa729a8,0xabd9a61f,
0x223eac00,0xa8722b64,0x2aa7a9a8,0xabd9261f,0xa8722c00,0x2bd9a61f,0xa23ea9a8,0xaaa72b64,0x2aa7ac00,0xa23ea61f,0xabd929a8,0xa8722b64,
0xabd92c00,0xaaa72b64,0xa87229a8,0xa23e261f,0xa23e0000,0xa872a61f,0xaaa7a9a8,0xabd9ab64,0x28720000,0x2bd92b64,0x223e29a8,0xaaa7a61f,
0xaaa70000,0xa23eab64,0x2bd929a8,0xa872261f,0x2bd90000,0xaaa7261f,0x2872a9a8,0xa23e2b64,0xabd90000,0x2aa7261f,0xa872a9a8,0x223e2b64,
0x2aa70000,0x223eab64,0xabd929a8,0x2872261f,0xa8720000,0xabd92b64,0xa23e29a8,0x2aa7a61f,0x223e0000,0x2872a61f,0x2aa7a9a8,0x2bd9ab64,
0x2bd9ac00,0x2aa7ab64,0x2872a9a8,0x223ea61f,0xaaa72c00,0x223e261f,0x2bd9a9a8,0x2872ab64,0x2872ac00,0xabd9261f,0x223e29a8,0x2aa7ab64,
0xa23e2c00,0x2872ab64,0xaaa729a8,0x2bd9a61f,0xa23eac00,0x28722b64,0xaaa7a9a8,0x2bd9261f,0x28722c00,0xabd9a61f,0x223ea9a8,0x2aa72b64,
0xaaa7ac00,0x223ea61f,0x2bd929a8,0x28722b64,0x2bd92c00,0x2aa72b64,0x287229a8,0x223e261f,0x223e0000,0x2872a61f,0x2aa7a9a8,0x2bd9ab64,
0xa8720000,0xabd92b64,0xa23e29a8,0x2aa7a61f,0x2aa70000,0x223eab64,0xabd929a8,0x2872261f,0xabd90000,0x2aa7261f,0xa872a9a8,0x223e2b64,
0x2bd90000,0xaaa7261f,0x2872a9a8,0xa23e2b64,0xaaa70000,0xa23eab64,0x2bd929a8,0xa872261f,0x28720000,0x2bd92b64,0x223e29a8,0xaaa7a61f,
0xa23e0000,0xa872a61f,0xaaa7a9a8,0xabd9ab64,0x27fe2800,0x96480000,0x273b2764,0xa2d7a21f,0x27ea27f6,0x9cb29a46,0x26dd270e,0xa41da38b,
0x27c327d9,0x9fc69e3e,0x266d26a7,0xa4c4a472,0x278827a8,0xa164a0a5,0x25ed262f,0xa55fa513,0x27c32800,0x9fc60000,0xa4c4a21f,0xa66da764,
0x25ed270e,0xa55fa38b,0xa73ba62f,0xa2d7a513,0x21642472,0xa788a6a7,0xa7fea7d9,0x16489e3e,0x9cb21a46,0xa7eaa7f6,0xa6dda7a8,0x241d20a5,
0x273b2800,0xa2d70000,0xa55fa764,0x25ed221f,0x1fc62513,0xa7c3a62f,0x1cb2a0a5,0x27ea27a8,0xa4c49e3e,0xa66da7d9,0x26dd2472,0x241d26a7,
0xa7fea70e,0x9648a38b,0x278827f6,0xa1641a46,0x266d2800,0xa4c40000,0x26dd221f,0x241d2764,0xa16420a5,0xa788a7a8,0x25ed27f6,0xa55f9a46,
0xa7fea6a7,0x1648a472,0xa2d71e3e,0xa73ba7d9,0x9fc6a62f,0x27c32513,0xa7eaa70e,0x1cb2a38b,0x255f2800,0xa5ed0000,0x21642764,0xa788a21f,
0xa66d9a46,0xa4c4a7f6,0xa7c3a38b,0x9fc6a70e,0xa41da7d9,0x26dd1e3e,0x9cb2a6a7,0x27ea2472,0x273b20a5,0x22d727a8,0x27fe2513,0x1648262f,
0x241d2800,0xa6dd0000,0xa7eaa21f,0x9cb2a764,0xa7fea38b,0x9648a70e,0x2164a513,0x2788262f,0x22d7a472,0x273b26a7,0x255f27d9,0xa5ed1e3e,
0x24c427f6,0xa66d1a46,0xa7c3a0a5,0x9fc6a7a8,0x21642800,0xa7880000,0x1648a764,0x27fe221f,0xa6dda62f,0x241da513,0x24c427a8,0xa66d20a5,
0x27ea1e3e,0x1cb227d9,0xa7c3a472,0x1fc6a6a7,0xa55f238b,0xa5eda70e,0x273b9a46,0x22d727f6,0x1cb22800,0xa7ea0000,0x27c3221f,0x9fc62764,
0xa2d7a7a8,0x273ba0a5,0xa7fe9a46,0x9648a7f6,0x255f26a7,0xa5ed2472,0x27889e3e,0x216427d9,0xa6dda513,0x241da62f,0xa66d238b,0xa4c4a70e,
0x96482800,0xa7fe0000,0xa2d72764,0xa73ba21f,0x1cb2a7f6,0x27ea1a46,0x241da70e,0x26dd238b,0x9fc627d9,0xa7c39e3e,0xa4c426a7,0xa66da472,
0x2164a7a8,0x278820a5,0x255fa62f,0x25ed2513,0x9fc62800,0xa7c30000,0xa66da21f,0x24c4a764,0x255fa70e,0x25ed238b,0x22d7262f,0xa73b2513,
0xa7882472,0xa164a6a7,0x1648a7d9,0x27fe9e3e,0x27ea9a46,0x9cb227f6,0xa41d27a8,0xa6dda0a5,0xa2d72800,0xa73b0000,0x25eda764,0x255f221f,
0x27c3a513,0x1fc6262f,0xa7ea20a5,0x1cb2a7a8,0xa66d9e3e,0x24c4a7d9,0x241d2472,0xa6dd26a7,0x1648270e,0xa7fe238b,0x2164a7f6,0x27889a46,
0xa4c42800,0xa66d0000,0x241d221f,0xa6dd2764,0x2788a0a5,0xa16427a8,0x255fa7f6,0x25ed1a46,0x1648a6a7,0x27fea472,0xa73b1e3e,0x22d7a7d9,
0xa7c3262f,0x9fc6a513,0x9cb2270e,0xa7ea238b,0xa5ed2800,0xa55f0000,0xa7882764,0xa164a21f,0x24c41a46,0xa66d27f6,0x1fc6238b,0xa7c3270e,
0x26dda7d9,0x241d1e3e,0x27eaa6a7,0x1cb22472,0xa2d7a0a5,0x273ba7a8,0x9648a513,0x27fea62f,0xa6dd2800,0xa41d0000,0x9cb2a21f,0x27eaa764,
0x1648238b,0xa7fe270e,0xa7882513,0x2164a62f,0x273ba472,0xa2d726a7,0xa5ed27d9,0xa55f1e3e,0x266da7f6,0x24c49a46,0x1fc620a5,0xa7c327a8,
0xa7882800,0xa1640000,0x27fea764,0x9648221f,0xa41d262f,0xa6dd2513,0x266da7a8,0x24c4a0a5,0x1cb21e3e,0xa7ea27d9,0x1fc6a472,0x27c3a6a7,
0x25eda38b,0xa55f270e,0xa2d71a46,0x273ba7f6,0xa7ea2800,0x9cb20000,0x9fc6221f,0xa7c32764,0xa73b27a8,0xa2d720a5,0x16481a46,0xa7fe27f6,
0xa5ed26a7,0xa55f2472,0x21649e3e,0xa78827d9,0xa41d2513,0xa6dd262f,0x24c4a38b,0xa66d270e,0xa7fe2800,0x16480000,0xa73b2764,0x22d7a21f,
0xa7ea27f6,0x1cb29a46,0xa6dd270e,0x241da38b,0xa7c327d9,0x1fc69e3e,0xa66d26a7,0x24c4a472,0xa78827a8,0x2164a0a5,0xa5ed262f,0x255fa513,
0xa7c32800,0x1fc60000,0x24c4a21f,0x266da764,0xa5ed270e,0x255fa38b,0x273ba62f,0x22d7a513,0xa1642472,0x2788a6a7,0x27fea7d9,0x96489e3e,
0x1cb21a46,0x27eaa7f6,0x26dda7a8,0xa41d20a5,0xa73b2800,0x22d70000,0x255fa764,0xa5ed221f,0x9fc62513,0x27c3a62f,0x9cb2a0a5,0xa7ea27a8,
0x24c49e3e,0x266da7d9,0xa6dd2472,0xa41d26a7,0x27fea70e,0x1648a38b,0xa78827f6,0x21641a46,0xa66d2800,0x24c40000,0xa6dd221f,0xa41d2764,
0x216420a5,0x2788a7a8,0xa5ed27f6,0x255f9a46,0x27fea6a7,0x9648a472,0x22d71e3e,0x273ba7d9,0x1fc6a62f,0xa7c32513,0x27eaa70e,0x9cb2a38b,
0xa55f2800,0x25ed0000,0xa1642764,0x2788a21f,0x266d9a46,0x24c4a7f6,0x27c3a38b,0x1fc6a70e,0x241da7d9,0xa6dd1e3e,0x1cb2a6a7,0xa7ea2472,
0xa73b20a5,0xa2d727a8,0xa7fe2513,0x9648262f,0xa41d2800,0x26dd0000,0x27eaa21f,0x1cb2a764,0x27fea38b,0x1648a70e,0xa164a513,0xa788262f,
0xa2d7a472,0xa73b26a7,0xa55f27d9,0x25ed1e3e,0xa4c427f6,0x266d1a46,0x27c3a0a5,0x1fc6a7a8,0xa1642800,0x27880000,0x9648a764,0xa7fe221f,
0x26dda62f,0xa41da513,0xa4c427a8,0x266d20a5,0xa7ea1e3e,0x9cb227d9,0x27c3a472,0x9fc6a6a7,0x255f238b,0x25eda70e,0xa73b9a46,0xa2d727f6,
0x9cb22800,0x27ea0000,0xa7c3221f,0x1fc62764,0x22d7a7a8,0xa73ba0a5,0x27fe9a46,0x1648a7f6,0xa55f26a7,0x25ed2472,0xa7889e3e,0xa16427d9,
0x26dda513,0xa41da62f,0x266d238b,0x24c4a70e,0x16482800,0x27fe0000,0x22d72764,0x273ba21f,0x9cb2a7f6,0xa7ea1a46,0xa41da70e,0xa6dd238b,
0x1fc627d9,0x27c39e3e,0x24c426a7,0x266da472,0xa164a7a8,0xa78820a5,0xa55fa62f,0xa5ed2513,0x1fc62800,0x27c30000,0x266da21f,0xa4c4a764,
0xa55fa70e,0xa5ed238b,0xa2d7262f,0x273b2513,0x27882472,0x2164a6a7,0x9648a7d9,0xa7fe9e3e,0xa7ea9a46,0x1cb227f6,0x241d27a8,0x26dda0a5,
0x22d72800,0x273b0000,0xa5eda764,0xa55f221f,0xa7c3a513,0x9fc6262f,0x27ea20a5,0x9cb2a7a8,0x266d9e3e,0xa4c4a7d9,0xa41d2472,0x26dd26a7,
0x9648270e,0x27fe238b,0xa164a7f6,0xa7889a46,0x24c42800,0x266d0000,0xa41d221f,0x26dd2764,0xa788a0a5,0x216427a8,0xa55fa7f6,0xa5ed1a46,
0x9648a6a7,0xa7fea472,0x273b1e3e,0xa2d7a7d9,0x27c3262f,0x1fc6a513,0x1cb2270e,0x27ea238b,0x25ed2800,0x255f0000,0x27882764,0x2164a21f,
0xa4c41a46,0x266d27f6,0x9fc6238b,0x27c3270e,0xa6dda7d9,0xa41d1e3e,0xa7eaa6a7,0x9cb22472,0x22d7a0a5,0xa73ba7a8,0x1648a513,0xa7fea62f,
0x26dd2800,0x241d0000,0x1cb2a21f,0xa7eaa764,0x9648238b,0x27fe270e,0x27882513,0xa164a62f,0xa73ba472,0x22d726a7,0x25ed27d9,0x255f1e3e,
0xa66da7f6,0xa4c49a46,0x9fc620a5,0x27c327a8,0x27882800,0x21640000,0xa7fea764,0x1648221f,0x241d262f,0x26dd2513,0xa66da7a8,0xa4c4a0a5,
0x9cb21e3e,0x27ea27d9,0x9fc6a472,0xa7c3a6a7,0xa5eda38b,0x255f270e,0x22d71a46,0xa73ba7f6,0x27ea2800,0x1cb20000,0x1fc6221f,0x27c32764,
0x273b27a8,0x22d720a5,0x96481a46,0x27fe27f6,0x25ed26a7,0x255f2472,0xa1649e3e,0x278827d9,0x241d2513,0x26dd262f,0xa4c4a38b,0x266d270e,
0x255f25a8,0xa5eda5a8,0x2164221f,0xa788a764,0x24c42513,0xa66da62f,0x1fc620a5,0xa7c3a7a8,0x241d2472,0xa6dda6a7,0x1cb21e3e,0xa7eaa7d9,
0x22d7238b,0xa73ba70e,0x16481a46,0xa7fea7f6,0xa41da5a8,0x26dd25a8,0x27ea2764,0x1cb2221f,0x9648a0a5,0x27fe27a8,0x278827f6,0xa1649a46,
0x22d71e3e,0x273b27d9,0x255f26a7,0xa5eda472,0x266d2513,0x24c4262f,0x1fc6238b,0xa7c3a70e,0x216425a8,0xa788a5a8,0x1648a21f,0x27fe2764,
0xa41d9a46,0xa6dda7f6,0x266d238b,0x24c4270e,0xa7eaa6a7,0x9cb2a472,0x27c327d9,0x9fc61e3e,0xa5eda7a8,0x255f20a5,0x22d7262f,0xa73ba513,
0x9cb2a5a8,0x27ea25a8,0xa7c3a764,0x1fc6a21f,0x273b238b,0x22d7270e,0x9648a513,0x27fe262f,0x255f27d9,0xa5ed9e3e,0x27882472,0x216426a7,
0xa41d1a46,0xa6dda7f6,0x24c427a8,0xa66da0a5,0x964825a8,0xa7fea5a8,0xa2d7221f,0xa73ba764,0xa7eaa62f,0x1cb2a513,0xa6dda7a8,0x241da0a5,
0x1fc6a472,0x27c326a7,0x24c49e3e,0x266d27d9,0x2788270e,0xa164238b,0x25ed27f6,0xa55f1a46,0x1fc6a5a8,0x27c325a8,0x266d2764,0xa4c4221f,
0x25ed27a8,0xa55f20a5,0xa73b9a46,0xa2d7a7f6,0xa7889e3e,0xa164a7d9,0x1648a6a7,0x27fe2472,0x1cb2a62f,0x27ea2513,0x26dd270e,0xa41d238b,
0xa2d725a8,0xa73ba5a8,0x25eda21f,0x255f2764,0x9fc6a7f6,0x27c31a46,0x9cb2270e,0xa7eaa38b,0x266d26a7,0xa4c42472,0xa41da7d9,0x26dd9e3e,
0xa7fea0a5,0x9648a7a8,0x27882513,0xa164262f,0x24c4a5a8,0x266d25a8,0xa41da764,0x26dda21f,0xa164270e,0xa788a38b,0x25ed262f,0xa55f2513,
0x1648a7d9,0x27fe1e3e,0xa73ba472,0x22d7a6a7,0x1fc627f6,0xa7c31a46,0x27ea20a5,0x9cb227a8,0xa5ed25a8,0xa55fa5a8,0xa788221f,0xa164a764,
0x266da513,0x24c4262f,0x27c3a0a5,0x1fc627a8,0xa6dd2472,0xa41da6a7,0xa7ea1e3e,0x9cb2a7d9,0x273ba38b,0x22d7270e,0x27fe9a46,0x164827f6,
0x26dda5a8,0x241d25a8,0x1cb22764,0xa7ea221f,0xa7fe20a5,0x9648a7a8,0x2164a7f6,0x27881a46,0x273b1e3e,0xa2d727d9,0xa5ed26a7,0xa55fa472,
0xa4c4a513,0x266da62f,0x27c3a38b,0x1fc6270e,0xa78825a8,0xa164a5a8,0x27fea21f,0x96482764,0x26dd1a46,0xa41d27f6,0xa4c4a38b,0x266da70e,
0x9cb2a6a7,0x27eaa472,0x9fc627d9,0xa7c31e3e,0xa55f27a8,0xa5eda0a5,0x273ba62f,0x22d72513,0x27eaa5a8,0x1cb225a8,0x1fc6a764,0x27c3a21f,
0xa2d7a38b,0x273ba70e,0xa7fe2513,0x9648a62f,0xa5ed27d9,0xa55f9e3e,0x21642472,0xa78826a7,0x26dd9a46,0xa41d27f6,0x266da7a8,0x24c420a5,
0xa7fe25a8,0x1648a5a8,0xa73b221f,0x22d7a764,0x9cb2262f,0xa7ea2513,0xa41d27a8,0xa6dd20a5,0x27c3a472,0x9fc626a7,0x266d9e3e,0xa4c427d9,
0x2164a70e,0x2788a38b,0x255fa7f6,0x25ed9a46,0x27c3a5a8,0x9fc625a8,0xa4c42764,0xa66d221f,0x255fa7a8,0x25eda0a5,0x22d71a46,0xa73b27f6,
0xa1649e3e,0x2788a7d9,0x27fea6a7,0x96482472,0xa7ea262f,0x1cb2a513,0x241da70e,0x26dda38b,0xa73b25a8,0x22d7a5a8,0x255fa21f,0xa5ed2764,
0xa7c327f6,0x9fc69a46,0x27eaa70e,0x9cb2238b,0xa4c426a7,0xa66d2472,0x26dda7d9,0x241d9e3e,0x164820a5,0xa7fe27a8,0x2164a513,0x2788a62f,
0x266da5a8,0xa4c425a8,0x26dda764,0x241da21f,0x2788a70e,0xa164238b,0x255fa62f,0x25eda513,0x27fea7d9,0x96481e3e,0x22d7a472,0x273ba6a7,
0x27c3a7f6,0x1fc69a46,0x1cb2a0a5,0x27eaa7a8,0xa55f25a8,0x25eda5a8,0xa164221f,0x2788a764,0xa4c42513,0x266da62f,0x9fc620a5,0x27c3a7a8,
0xa41d2472,0x26dda6a7,0x9cb21e3e,0x27eaa7d9,0xa2d7238b,0x273ba70e,0x96481a46,0x27fea7f6,0x241da5a8,0xa6dd25a8,0xa7ea2764,0x9cb2221f,
0x1648a0a5,0xa7fe27a8,0xa78827f6,0x21649a46,0xa2d71e3e,0xa73b27d9,0xa55f26a7,0x25eda472,0xa66d2513,0xa4c4262f,0x9fc6238b,0x27c3a70e,
0xa16425a8,0x2788a5a8,0x9648a21f,0xa7fe2764,0x241d9a46,0x26dda7f6,0xa66d238b,0xa4c4270e,0x27eaa6a7,0x1cb2a472,0xa7c327d9,0x1fc61e3e,
0x25eda7a8,0xa55f20a5,0xa2d7262f,0x273ba513,0x1cb2a5a8,0xa7ea25a8,0x27c3a764,0x9fc6a21f,0xa73b238b,0xa2d7270e,0x1648a513,0xa7fe262f,
0xa55f27d9,0x25ed9e3e,0xa7882472,0xa16426a7,0x241d1a46,0x26dda7f6,0xa4c427a8,0x266da0a5,0x164825a8,0x27fea5a8,0x22d7221f,0x273ba764,
0x27eaa62f,0x9cb2a513,0x26dda7a8,0xa41da0a5,0x9fc6a472,0xa7c326a7,0xa4c49e3e,0xa66d27d9,0xa788270e,0x2164238b,0xa5ed27f6,0x255f1a46,
0x9fc6a5a8,0xa7c325a8,0xa66d2764,0x24c4221f,0xa5ed27a8,0x255f20a5,0x273b9a46,0x22d7a7f6,0x27889e3e,0x2164a7d9,0x9648a6a7,0xa7fe2472,
0x9cb2a62f,0xa7ea2513,0xa6dd270e,0x241d238b,0x22d725a8,0x273ba5a8,0xa5eda21f,0xa55f2764,0x1fc6a7f6,0xa7c31a46,0x1cb2270e,0x27eaa38b,
0xa66d26a7,0x24c42472,0x241da7d9,0xa6dd9e3e,0x27fea0a5,0x1648a7a8,0xa7882513,0x2164262f,0xa4c4a5a8,0xa66d25a8,0x241da764,0xa6dda21f,
0x2164270e,0x2788a38b,0xa5ed262f,0x255f2513,0x9648a7d9,0xa7fe1e3e,0x273ba472,0xa2d7a6a7,0x9fc627f6,0x27c31a46,0xa7ea20a5,0x1cb227a8,
0x25ed25a8,0x255fa5a8,0x2788221f,0x2164a764,0xa66da513,0xa4c4262f,0xa7c3a0a5,0x9fc627a8,0x26dd2472,0x241da6a7,0x27ea1e3e,0x1cb2a7d9,
0xa73ba38b,0xa2d7270e,0xa7fe9a46,0x964827f6,0xa6dda5a8,0xa41d25a8,0x9cb22764,0x27ea221f,0x27fe20a5,0x1648a7a8,0xa164a7f6,0xa7881a46,
0xa73b1e3e,0x22d727d9,0x25ed26a7,0x255fa472,0x24c4a513,0xa66da62f,0xa7c3a38b,0x9fc6270e,0x278825a8,0x2164a5a8,0xa7fea21f,0x16482764,
0xa6dd1a46,0x241d27f6,0x24c4a38b,0xa66da70e,0x1cb2a6a7,0xa7eaa472,0x1fc627d9,0x27c31e3e,0x255f27a8,0x25eda0a5,0xa73ba62f,0xa2d72513,
0xa7eaa5a8,0x9cb225a8,0x9fc6a764,0xa7c3a21f,0x22d7a38b,0xa73ba70e,0x27fe2513,0x1648a62f,0x25ed27d9,0x255f9e3e,0xa1642472,0x278826a7,
0xa6dd9a46,0x241d27f6,0xa66da7a8,0xa4c420a5,0x27fe25a8,0x9648a5a8,0x273b221f,0xa2d7a764,0x1cb2262f,0x27ea2513,0x241d27a8,0x26dd20a5,
0xa7c3a472,0x1fc626a7,0xa66d9e3e,0x24c427d9,0xa164a70e,0xa788a38b,0xa55fa7f6,0xa5ed9a46,0xa7c3a5a8,0x1fc625a8,0x24c42764,0x266d221f,
0xa55fa7a8,0xa5eda0a5,0xa2d71a46,0x273b27f6,0x21649e3e,0xa788a7d9,0xa7fea6a7,0x16482472,0x27ea262f,0x9cb2a513,0xa41da70e,0xa6dda38b,
0x273b25a8,0xa2d7a5a8,0xa55fa21f,0x25ed2764,0x27c327f6,0x1fc69a46,0xa7eaa70e,0x1cb2238b,0x24c426a7,0x266d2472,0xa6dda7d9,0xa41d9e3e,
0x964820a5,0x27fe27a8,0xa164a513,0xa788a62f,0xa66da5a8,0x24c425a8,0xa6dda764,0xa41da21f,0xa788a70e,0x2164238b,0xa55fa62f,0xa5eda513,
0xa7fea7d9,0x16481e3e,0xa2d7a472,0xa73ba6a7,0xa7c3a7f6,0x9fc69a46,0x9cb2a0a5,0xa7eaa7a8,
};

#define PROF(slot) do {} while (0)
#define PROF3(slot) do {} while (0)
#define PROF2(slot) do {} while (0)

__device__ __forceinline__ uint32_t smem_u32(const void* p) { return (uint32_t)__cvta_generic_to_shared(p); }

__device__ __forceinline__ void mbar_init(uint32_t a, uint32_t c) {
  asm volatile("mbarrier.init.shared::cta.b64 [%0], %1;\n" ::"r"(a), "r"(c) : "memory");
}
__device__ __forceinline__ void mbar_expect_tx(uint32_t a, uint32_t bytes) {
  asm volatile("mbarrier.arrive.expect_tx.shared::cta.b64 _, [%0], %1;\n" ::"r"(a), "r"(bytes) : "memory");
}
__device__ __forceinline__ void mbar_arrive_cluster(uint32_t cluster_addr) {
  asm volatile("mbarrier.arrive.shared::cluster.b64 _, [%0];\n" ::"r"(cluster_addr) : "memory");
}
__device__ __forceinline__ void mbar_arrive_cluster_n(uint32_t cluster_addr, uint32_t n) {
  asm volatile("mbarrier.arrive.shared::cluster.b64 _, [%0], %1;\n" ::"r"(cluster_addr), "r"(n) : "memory");
}
__device__ __forceinline__ bool mbar_try(uint32_t a, uint32_t parity) {
  uint32_t ok;
  asm volatile("{\n.reg .pred p;\nmbarrier.try_wait.parity.shared::cta.b64 p, [%1], %2;\nselp.u32 %0, 1, 0, p;\n}\n"
               : "=r"(ok) : "r"(a), "r"(parity) : "memory");
  return ok;
}
__device__ __forceinline__ void mbar_wait(uint32_t a, uint32_t parity) {
  if (mbar_try(a, parity)) return;
#pragma unroll 1
  for (int n = 0; n < SPIN_LIMIT; n++)
    if (mbar_try(a, parity)) break;
}
__device__ __forceinline__ void mbar_wait_idle(uint32_t a, uint32_t parity) {
#pragma unroll 1
  for (int n = 0; n < SPIN_LIMIT; n++) {
    uint32_t ok;
    asm volatile("{\n.reg .pred p;\nmbarrier.try_wait.parity.shared::cta.b64 p, [%1], %2, %3;\nselp.u32 %0, 1, 0, p;\n}\n"
                 : "=r"(ok) : "r"(a), "r"(parity), "r"(4000) : "memory");
    if (ok) break;
  }
}
__device__ __forceinline__ bool elect_one() {
  uint32_t p;
  asm volatile("{\n.reg .pred P;\nelect.sync _|P, 0xffffffff;\nselp.u32 %0, 1, 0, P;\n}\n" : "=r"(p));
  return p;
}
__device__ __forceinline__ uint32_t mapa(uint32_t a, uint32_t rank) {
  uint32_t r;
  asm volatile("mapa.shared::cluster.u32 %0, %1, %2;\n" : "=r"(r) : "r"(a), "r"(rank));
  return r;
}
__device__ __forceinline__ void nb_sync(int id, int n) { asm volatile("bar.sync %0, %1;\n" ::"r"(id), "r"(n) : "memory"); }
__device__ __forceinline__ void nb_arrive(int id, int n) { asm volatile("bar.arrive %0, %1;\n" ::"r"(id), "r"(n) : "memory"); }
__device__ __forceinline__ void cluster_sync_all() {
  asm volatile("barrier.cluster.arrive.relaxed.aligned;\nbarrier.cluster.wait.aligned;\n" ::: "memory");
}
__device__ __forceinline__ void fence_async_smem() { asm volatile("fence.proxy.async.shared::cta;\n" ::: "memory"); }
__device__ __forceinline__ void fence_async_all() { asm volatile("fence.proxy.async.global;\n" ::: "memory"); }

__device__ __forceinline__ void tma_load_3d(uint32_t dst, const CUtensorMap* tm, uint32_t bar, int c0, int c1, int c2) {
  asm volatile(
      "cp.async.bulk.tensor.3d.shared::cluster.global.mbarrier::complete_tx::bytes [%0], [%1, {%3, %4, %5}], [%2];\n"
      ::"r"(dst), "l"(tm), "r"(bar), "r"(c0), "r"(c1), "r"(c2) : "memory");
}
__device__ __forceinline__ void tma_load_4d(uint32_t dst, const CUtensorMap* tm, uint32_t bar, int c0, int c1, int c2, int c3) {
  asm volatile(
      "cp.async.bulk.tensor.4d.shared::cluster.global.mbarrier::complete_tx::bytes [%0], [%1, {%3, %4, %5, %6}], [%2];\n"
      ::"r"(dst), "l"(tm), "r"(bar), "r"(c0), "r"(c1), "r"(c2), "r"(c3) : "memory");
}
__device__ __forceinline__ void tma_load_3d_mc(uint32_t dst, const CUtensorMap* tm, uint32_t bar, int c0, int c1, int c2) {
  asm volatile(
      "cp.async.bulk.tensor.3d.shared::cluster.global.mbarrier::complete_tx::bytes.multicast::cluster [%0], [%1, {%3, %4, %5}], [%2], %6;\n"
      ::"r"(dst), "l"(tm), "r"(bar), "r"(c0), "r"(c1), "r"(c2), "h"((uint16_t)3) : "memory");
}
__device__ __forceinline__ void tma_load_5d(uint32_t dst, const CUtensorMap* tm, uint32_t bar, int c0, int c4) {
  asm volatile(
      "cp.async.bulk.tensor.5d.shared::cluster.global.mbarrier::complete_tx::bytes [%0], [%1, {%3, %5, %5, %5, %4}], [%2];\n"
      ::"r"(dst), "l"(tm), "r"(bar), "r"(c0), "r"(c4), "r"(0) : "memory");
}
__device__ __forceinline__ void bulk_load(uint32_t dst, const void* src, uint32_t bytes, uint32_t bar) {
  asm volatile("cp.async.bulk.shared::cluster.global.mbarrier::complete_tx::bytes [%0], [%1], %2, [%3];\n"
               ::"r"(dst), "l"(src), "r"(bytes), "r"(bar) : "memory");
}
__device__ __forceinline__ void bulk_commit() { asm volatile("cp.async.bulk.commit_group;\n" ::: "memory"); }
__device__ __forceinline__ void bulk_wait0() { asm volatile("cp.async.bulk.wait_group 0;\n" ::: "memory"); }
__device__ __forceinline__ void prefetch_tmap(const CUtensorMap* tm) {
  asm volatile("prefetch.tensormap [%0];\n" ::"l"(tm) : "memory");
}

__device__ __forceinline__ void wg_fence() { asm volatile("wgmma.fence.sync.aligned;\n" ::: "memory"); }
__device__ __forceinline__ void wg_commit() { asm volatile("wgmma.commit_group.sync.aligned;\n" ::: "memory"); }
template <int N> __device__ __forceinline__ void wg_wait() {
  asm volatile("wgmma.wait_group.sync.aligned %0;\n" ::"n"(N) : "memory");
}
__device__ __forceinline__ uint64_t mkdesc(uint32_t addr, uint32_t lbo, uint32_t sbo, uint32_t swz) {
  return (uint64_t)((addr & 0x3FFFF) >> 4) | ((uint64_t)(lbo >> 4) << 16) | ((uint64_t)(sbo >> 4) << 32) |
         ((uint64_t)swz << 62);
}

#define R4(d, o) "+f"(d[o + 0]), "+f"(d[o + 1]), "+f"(d[o + 2]), "+f"(d[o + 3])
#define R8(d, o) R4(d, o), R4(d, o + 4)
#define R16(d, o) R8(d, o), R8(d, o + 8)
#define R32(d, o) R16(d, o), R16(d, o + 16)
#define R64(d, o) R32(d, o), R32(d, o + 32)

__device__ __forceinline__ void wgmma_n192(float (&d)[96], uint64_t da, uint64_t db, uint32_t acc) {
  asm volatile(
      "{\n.reg .pred p;\nsetp.ne.u32 p, %98, 0;\n"
      "wgmma.mma_async.sync.aligned.m64n192k16.f32.bf16.bf16 "
      "{%0,%1,%2,%3,%4,%5,%6,%7,%8,%9,%10,%11,%12,%13,%14,%15,%16,%17,%18,%19,%20,%21,%22,%23,%24,%25,%26,%27,%28,%29,%30,%31,"
      "%32,%33,%34,%35,%36,%37,%38,%39,%40,%41,%42,%43,%44,%45,%46,%47,%48,%49,%50,%51,%52,%53,%54,%55,%56,%57,%58,%59,%60,%61,%62,%63,"
      "%64,%65,%66,%67,%68,%69,%70,%71,%72,%73,%74,%75,%76,%77,%78,%79,%80,%81,%82,%83,%84,%85,%86,%87,%88,%89,%90,%91,%92,%93,%94,%95}, "
      "%96, %97, p, 1, 1, 0, 1;\n}\n"
      : R64(d, 0), R32(d, 64)
      : "l"(da), "l"(db), "r"(acc));
}
__device__ __forceinline__ void wgmma_n128(float (&d)[64], uint64_t da, uint64_t db, uint32_t acc) {
  asm volatile(
      "{\n.reg .pred p;\nsetp.ne.u32 p, %66, 0;\n"
      "wgmma.mma_async.sync.aligned.m64n128k16.f32.bf16.bf16 "
      "{%0,%1,%2,%3,%4,%5,%6,%7,%8,%9,%10,%11,%12,%13,%14,%15,%16,%17,%18,%19,%20,%21,%22,%23,%24,%25,%26,%27,%28,%29,%30,%31,"
      "%32,%33,%34,%35,%36,%37,%38,%39,%40,%41,%42,%43,%44,%45,%46,%47,%48,%49,%50,%51,%52,%53,%54,%55,%56,%57,%58,%59,%60,%61,%62,%63}, "
      "%64, %65, p, 1, 1, 0, 1;\n}\n"
      : R64(d, 0)
      : "l"(da), "l"(db), "r"(acc));
}
template <int N> __device__ __forceinline__ void fence_regs(float (&d)[N]) {
#pragma unroll
  for (int i = 0; i < N; i++) asm volatile("" : "+f"(d[i])::"memory");
}

__device__ __forceinline__ void mma16816(float (&d)[4], uint32_t a0, uint32_t a1, uint32_t a2, uint32_t a3, uint32_t b0,
                                         uint32_t b1) {
  asm("mma.sync.aligned.m16n8k16.row.col.f32.bf16.bf16.f32 {%0,%1,%2,%3}, {%4,%5,%6,%7}, {%8,%9}, {%0,%1,%2,%3};\n"
      : "+f"(d[0]), "+f"(d[1]), "+f"(d[2]), "+f"(d[3])
      : "r"(a0), "r"(a1), "r"(a2), "r"(a3), "r"(b0), "r"(b1));
}
__device__ __forceinline__ void mma16816_z(float (&d)[4], uint32_t a0, uint32_t a1, uint32_t a2, uint32_t a3, uint32_t b0,
                                           uint32_t b1) {
  asm("mma.sync.aligned.m16n8k16.row.col.f32.bf16.bf16.f32 {%0,%1,%2,%3}, {%4,%5,%6,%7}, {%8,%9}, {%10,%10,%10,%10};\n"
      : "=f"(d[0]), "=f"(d[1]), "=f"(d[2]), "=f"(d[3])
      : "r"(a0), "r"(a1), "r"(a2), "r"(a3), "r"(b0), "r"(b1), "f"(0.f));
}
__device__ __forceinline__ void ldsm4t(uint32_t (&r)[4], uint32_t a) {
  asm volatile("ldmatrix.sync.aligned.m8n8.x4.trans.shared.b16 {%0,%1,%2,%3}, [%4];\n"
               : "=r"(r[0]), "=r"(r[1]), "=r"(r[2]), "=r"(r[3]) : "r"(a) : "memory");
}
__device__ __forceinline__ void ldsm2t(uint32_t& r0, uint32_t& r1, uint32_t a) {
  asm volatile("ldmatrix.sync.aligned.m8n8.x2.trans.shared.b16 {%0,%1}, [%2];\n" : "=r"(r0), "=r"(r1) : "r"(a) : "memory");
}
__device__ __forceinline__ void st_async128(uint32_t a, uint32_t bar, uint32_t x, uint32_t y, uint32_t z, uint32_t w) {
  asm volatile("st.async.weak.shared::cluster.mbarrier::complete_tx::bytes.v4.b32 [%0], {%2,%3,%4,%5}, [%1];\n"
               ::"r"(a), "r"(bar), "r"(x), "r"(y), "r"(z), "r"(w) : "memory");
}
__device__ __forceinline__ void mbar_arrive(uint32_t a) {
  asm volatile("mbarrier.arrive.shared::cta.b64 _, [%0];\n" ::"r"(a) : "memory");
}
__device__ __forceinline__ void stsm4(uint32_t a, uint32_t r0, uint32_t r1, uint32_t r2, uint32_t r3) {
  asm volatile("stmatrix.sync.aligned.m8n8.x4.shared.b16 [%0], {%1,%2,%3,%4};\n"
               ::"r"(a), "r"(r0), "r"(r1), "r"(r2), "r"(r3) : "memory");
}
__device__ __forceinline__ void stsm4t(uint32_t a, uint32_t r0, uint32_t r1, uint32_t r2, uint32_t r3) {
  asm volatile("stmatrix.sync.aligned.m8n8.x4.trans.shared.b16 [%0], {%1,%2,%3,%4};\n"
               ::"r"(a), "r"(r0), "r"(r1), "r"(r2), "r"(r3) : "memory");
}
__device__ __forceinline__ uint2 lds64(uint32_t a) {
  uint2 v;
  asm volatile("ld.shared.v2.u32 {%0,%1}, [%2];\n" : "=r"(v.x), "=r"(v.y) : "r"(a));
  return v;
}
__device__ __forceinline__ uint4 lds128(uint32_t a) {
  uint4 v;
  asm volatile("ld.shared.v4.u32 {%0,%1,%2,%3}, [%4];\n" : "=r"(v.x), "=r"(v.y), "=r"(v.z), "=r"(v.w) : "r"(a) : "memory");
  return v;
}
__device__ __forceinline__ void sts128(uint32_t a, uint32_t x, uint32_t y, uint32_t z, uint32_t w) {
  asm volatile("st.shared.v4.u32 [%0], {%1,%2,%3,%4};\n" ::"r"(a), "r"(x), "r"(y), "r"(z), "r"(w) : "memory");
}
__device__ __forceinline__ uint32_t pack_bf16(float lo, float hi) {
  uint32_t r;
  asm("cvt.rn.bf16x2.f32 %0, %1, %2;\n" : "=r"(r) : "f"(hi), "f"(lo));
  return r;
}
__device__ __forceinline__ uint32_t bmul2(uint32_t a, uint32_t b) {
  uint32_t r;
  asm("mul.rn.bf16x2 %0, %1, %2;\n" : "=r"(r) : "r"(a), "r"(b));
  return r;
}
__device__ __forceinline__ uint32_t bmax2(uint32_t a, uint32_t b) {
  uint32_t r;
  asm("max.bf16x2 %0, %1, %2;\n" : "=r"(r) : "r"(a), "r"(b));
  return r;
}
__device__ __forceinline__ uint32_t bfma2(uint32_t a, uint32_t b, uint32_t c) {
  uint32_t r;
  asm("fma.rn.bf16x2 %0, %1, %2, %3;\n" : "=r"(r) : "r"(a), "r"(b), "r"(c));
  return r;
}
__device__ __forceinline__ uint32_t badd2(uint32_t a, uint32_t b) {
  uint32_t r;
  asm("add.rn.bf16x2 %0, %1, %2;\n" : "=r"(r) : "r"(a), "r"(b));
  return r;
}
__device__ __forceinline__ void prefetch_l2(const void* p) { asm volatile("prefetch.global.L2 [%0];\n" ::"l"(p)); }
__device__ __forceinline__ void cp_async16n(uint32_t dst, const void* src) {
  asm volatile("cp.async.cg.shared.global [%0], [%1], 16;\n" ::"r"(dst), "l"(src) : "memory");
}
__device__ __forceinline__ void cp_async16(uint32_t dst, const void* src, uint32_t srcbytes) {
  asm volatile("cp.async.cg.shared.global.L2::256B [%0], [%1], 16, %2;\n" ::"r"(dst), "l"(src), "r"(srcbytes) : "memory");
}
__device__ __forceinline__ uint32_t ld_acquire(const uint32_t* p) {
  uint32_t v;
  asm volatile("ld.acquire.gpu.global.u32 %0, [%1];\n" : "=r"(v) : "l"(p) : "memory");
  return v;
}
__device__ __forceinline__ uint32_t ld_relaxed(const uint32_t* p) {
  uint32_t v;
  asm volatile("ld.relaxed.gpu.global.u32 %0, [%1];\n" : "=r"(v) : "l"(p) : "memory");
  return v;
}
__device__ __forceinline__ void st_release(uint32_t* p, uint32_t v) {
  asm volatile("st.release.gpu.global.u32 [%0], %1;\n" ::"l"(p), "r"(v) : "memory");
}
__device__ __forceinline__ void wait_flag(const uint32_t* p, uint32_t want) {
  int n = 0;
  while (ld_relaxed(p) != want && ++n < SPIN_LIMIT) __nanosleep(40);
  (void)ld_acquire(p);
}

struct Params {
  const __nv_bfloat16* x;
  const __nv_bfloat16* w;
  const __nv_bfloat16* q;
  const __nv_bfloat16* k;
  const __nv_bfloat16* v;
  const __nv_bfloat16* shift_k;
  const __nv_bfloat16* ssm_k;
  const __nv_bfloat16* ssm_D;
  const __nv_bfloat16* wo;
  __nv_bfloat16* out;
};

__device__ __forceinline__ uint32_t lds32(uint32_t a) {
  uint32_t v;
  asm volatile("ld.shared.u32 %0, [%1];\n" : "=r"(v) : "r"(a));
  return v;
}
#define W4(d, o) "=f"(d[o + 0]), "=f"(d[o + 1]), "=f"(d[o + 2]), "=f"(d[o + 3])
#define W8(d, o) W4(d, o), W4(d, o + 4)
#define W16(d, o) W8(d, o), W8(d, o + 8)
#define U4(c, d, o) c(d[o + 0]), c(d[o + 1]), c(d[o + 2]), c(d[o + 3])
#define U8(c, d, o) U4(c, d, o), U4(c, d, o + 4)
#define U16(c, d, o) U8(c, d, o), U8(c, d, o + 8)
#define U32(c, d, o) U16(c, d, o), U16(c, d, o + 16)
#define D32 "{%0,%1,%2,%3,%4,%5,%6,%7,%8,%9,%10,%11,%12,%13,%14,%15,%16,%17,%18,%19,%20,%21,%22,%23,%24,%25,%26,%27,%28,%29,%30,%31}"
#define D16 "{%0,%1,%2,%3,%4,%5,%6,%7,%8,%9,%10,%11,%12,%13,%14,%15}"
#define D8 "{%0,%1,%2,%3,%4,%5,%6,%7}"
template <int ACC> __device__ __forceinline__ void hmma_n128t(uint32_t (&d)[32], const uint32_t (&a)[4], uint64_t db) {
  if (ACC)
    asm volatile("wgmma.mma_async.sync.aligned.m64n128k16.f16.f16.f16 " D32 ", {%32,%33,%34,%35}, %36, 1, 1, 1, 1;\n"
                 : U32("+r", d, 0) : "r"(a[0]), "r"(a[1]), "r"(a[2]), "r"(a[3]), "l"(db));
  else
    asm volatile("wgmma.mma_async.sync.aligned.m64n128k16.f16.f16.f16 " D32 ", {%32,%33,%34,%35}, %36, 0, 1, 1, 1;\n"
                 : U32("=r", d, 0) : "r"(a[0]), "r"(a[1]), "r"(a[2]), "r"(a[3]), "l"(db));
}
template <int ACC, int TB> __device__ __forceinline__ void hmma_n32(uint32_t (&d)[8], const uint32_t (&a)[4], uint64_t db) {
  if (ACC)
    asm volatile("wgmma.mma_async.sync.aligned.m64n32k16.f16.f16.f16 " D8 ", {%8,%9,%10,%11}, %12, 1, 1, 1, %13;\n"
                 : U8("+r", d, 0) : "r"(a[0]), "r"(a[1]), "r"(a[2]), "r"(a[3]), "l"(db), "n"(TB));
  else
    asm volatile("wgmma.mma_async.sync.aligned.m64n32k16.f16.f16.f16 " D8 ", {%8,%9,%10,%11}, %12, 0, 1, 1, %13;\n"
                 : U8("=r", d, 0) : "r"(a[0]), "r"(a[1]), "r"(a[2]), "r"(a[3]), "l"(db), "n"(TB));
}
template <int N> __device__ __forceinline__ void fence_regs(uint32_t (&d)[N]) {
#pragma unroll
  for (int i = 0; i < N; i++) asm volatile("" : "+r"(d[i])::"memory");
}
__device__ __forceinline__ uint32_t hmul(uint32_t a, uint32_t b) { uint32_t r; asm("mul.rn.f16x2 %0, %1, %2;\n" : "=r"(r) : "r"(a), "r"(b)); return r; }
__device__ __forceinline__ uint32_t hadd(uint32_t a, uint32_t b) { uint32_t r; asm("add.rn.f16x2 %0, %1, %2;\n" : "=r"(r) : "r"(a), "r"(b)); return r; }
__device__ __forceinline__ uint32_t hsub(uint32_t a, uint32_t b) { uint32_t r; asm("sub.rn.f16x2 %0, %1, %2;\n" : "=r"(r) : "r"(a), "r"(b)); return r; }
__device__ __forceinline__ uint32_t hfma(uint32_t a, uint32_t b, uint32_t c) { uint32_t r; asm("fma.rn.f16x2 %0, %1, %2, %3;\n" : "=r"(r) : "r"(a), "r"(b), "r"(c)); return r; }
__device__ __forceinline__ uint32_t hfnma(uint32_t a, uint32_t b, uint32_t c) {
  uint32_t r;
  asm("{\n.reg .b32 t;\nneg.f16x2 t, %1;\nfma.rn.f16x2 %0, t, %2, %3;\n}\n" : "=r"(r) : "r"(a), "r"(b), "r"(c));
  return r;
}
__device__ __forceinline__ uint32_t hrefl(uint32_t p, uint32_t s) {
  uint32_t r;
  asm("{\n.reg .b32 t;\nneg.f16x2 t, %2;\nfma.rn.f16x2 %0, %1, %3, t;\n}\n" : "=r"(r) : "r"(p), "r"(s), "r"(0x40004000u));
  return r;
}
__device__ __forceinline__ void bfly(uint32_t xr, uint32_t xi, uint32_t tr, uint32_t ti, uint32_t yr, uint32_t yi, uint32_t ur,
                                     uint32_t ui, uint32_t& sr, uint32_t& si, uint32_t& dr, uint32_t& di) {
  const uint32_t pr = hfnma(xi, ti, hmul(xr, tr)), pi = hfma(xi, tr, hmul(xr, ti));
  sr = hfnma(yi, ui, hfma(yr, ur, pr));
  si = hfma(yi, ur, hfma(yr, ui, pi));
  dr = hrefl(pr, sr);
  di = hrefl(pi, si);
}
template <int BH> __device__ __forceinline__ void fft_e1(const uint32_t (&d)[32], const uint32_t (&tw)[16], uint32_t (&a2)[2][2][4]) {
#pragma unroll
  for (int be = 0; be < 2; be++)
#pragma unroll
    for (int s = 0; s < 2; s++) {
      const int o = 16 * s + 8 * be + 2 * BH, p = 2 * BH;
      bfly(d[o], d[o + 1], tw[p], tw[p + 1], d[o + 4], d[o + 5], tw[p + 4], tw[p + 5], a2[be][0][s], a2[be][0][2 + s],
           a2[be][1][s], a2[be][1][2 + s]);
    }
}
__device__ __forceinline__ uint32_t hfms(uint32_t a, uint32_t b, uint32_t c) {
  uint32_t r;
  asm("{\n.reg .b32 t;\nneg.f16x2 t, %3;\nfma.rn.f16x2 %0, %1, %2, t;\n}\n" : "=r"(r) : "r"(a), "r"(b), "r"(c));
  return r;
}
template <int C, int J> __device__ __forceinline__ void fft_e2(const uint32_t (&d0)[8], const uint32_t (&d1)[8], uint32_t (&a3)[2][4]) {
  const uint32_t ur = d0[2 * J], ui = d0[4 + 2 * J], hr = d0[2 * J + 1], hi = d0[5 + 2 * J];
  const uint32_t vr = d1[2 * J], vi = d1[4 + 2 * J], gr = d1[2 * J + 1], gi = d1[5 + 2 * J];
  const uint32_t pr = hfnma(ui, hi, hmul(ur, hr)), pi = hfma(ui, hr, hmul(ur, hi));
  a3[0][2 + C] = pr;
  a3[0][C] = pi;
  a3[1][2 + C] = hfnma(vi, hi, hfma(vr, hr, hfnma(ui, gi, hfms(ur, gr, pi))));
  a3[1][C] = hfma(vi, hr, hfma(vr, hi, hfma(ui, gr, hfma(ur, gi, pr))));
}
__device__ __forceinline__ void fft_e3(const uint32_t (&d)[2][8], const uint32_t (&tw)[16], uint32_t zaddr) {
#pragma unroll
  for (int rho = 0; rho < 2; rho++) {
    uint32_t zr[4], zi[4];
#pragma unroll
    for (int nb = 0; nb < 4; nb++) {
      const uint32_t xi = d[nb >> 1][2 * (nb & 1) + rho], xr = d[nb >> 1][4 + 2 * (nb & 1) + rho];
      const uint32_t tr = tw[8 + 4 * rho + 2 * (nb & 1)], ti = tw[9 + 4 * rho + 2 * (nb & 1)];
      zr[nb] = hfnma(xi, ti, hmul(xr, tr));
      zi[nb] = hfma(xi, tr, hmul(xr, ti));
    }
    stsm4(zaddr + rho * 1024, zr[0], zr[1], zr[2], zr[3]);
    stsm4(zaddr + rho * 1024 + 512, zi[0], zi[1], zi[2], zi[3]);
  }
}
__device__ __forceinline__ float bf_lo(uint32_t v) {
  uint32_t r;
  asm("prmt.b32 %0, %1, 0, 0x1044;\n" : "=r"(r) : "r"(v));
  return __uint_as_float(r);
}
__device__ __forceinline__ float bf_hi(uint32_t v) { return __uint_as_float(v & 0xffff0000u); }
__device__ __forceinline__ float ex2(float x) {
  float r;
  asm("ex2.approx.ftz.f32 %0, %1;\n" : "=f"(r) : "f"(x));
  return r;
}
__device__ __forceinline__ float rcp(float x) {
  float r;
  asm("rcp.approx.ftz.f32 %0, %1;\n" : "=f"(r) : "f"(x));
  return r;
}

__device__ __forceinline__ int g2_a(int s) { return ((0xA1054 >> (4 * s)) & 15) * 16384; }
__device__ __forceinline__ int g2_b(int s) { return ((0xCDB32 >> (4 * s)) & 15) * 16384; }
static_assert(OFF_U == 10 * 16384 && OFF_H == 12 * 16384 && OFF_OP == 4 * 16384, "units");
__device__ __forceinline__ int g2_k(int hp, int i) {
  return i < 2 ? hp ^ 1 ^ i : i < 4 ? (hp & ~1) ^ i : ((hp & ~3) + i) & 15; }
__device__ __forceinline__ int y_slot(int wg, int it) {
  static_assert(T_B2 == T_TW + 8192 && T_A1 == T_B2 + 4096, "y slots");
  return OFF_T + T_TW + ((it + 3) & 3) * 4096 + wg * 2048;
}

__device__ __forceinline__ void to_arr(uint32_t (&d)[4], uint4 v) { d[0] = v.x; d[1] = v.y; d[2] = v.z; d[3] = v.w; }

__device__ __forceinline__ void attn_stage(uint32_t sb, int blk, int lane, const float (&acc)[96], uint32_t (&k1)[2][4]) {
  const int lr = lane & 7, lm = lane >> 3;
  const uint32_t base = sb + OFF_VP + (blk * 16 + lr + 8 * (lm & 1)) * 128;
#pragma unroll
  for (int i = 0; i < 8; i++) k1[i >> 2][i & 3] = pack_bf16(acc[34 + 4 * i], acc[35 + 4 * i]);
  const uint32_t kh = sb + OFF_KH + blk * 2048 + lane * 16;
  sts128(kh, k1[0][0], k1[0][1], k1[0][2], k1[0][3]);
  sts128(kh + 512, k1[1][0], k1[1][1], k1[1][2], k1[1][3]);
#pragma unroll
  for (int j = 0; j < 8; j += 2)
    stsm4(base + (((j + (lm >> 1)) ^ lr) << 4), pack_bf16(acc[64 + 4 * j], acc[65 + 4 * j]),
          pack_bf16(acc[66 + 4 * j], acc[67 + 4 * j]), pack_bf16(acc[68 + 4 * j], acc[69 + 4 * j]),
          pack_bf16(acc[70 + 4 * j], acc[71 + 4 * j]));
}
__device__ __forceinline__ void attn_pack(const float (&acc)[96], uint32_t (&qa)[2][8], uint32_t (&k0)[2][4]) {
#pragma unroll
  for (int hd = 0; hd < 2; hd++) {
#pragma unroll
    for (int i = 0; i < 8; i++) {
      asm volatile("cvt.rn.bf16x2.f32 %0, %1, %2;\n" : "=r"(qa[hd][i]) : "f"(acc[16 * hd + 2 * i + 1]), "f"(acc[16 * hd + 2 * i]));
    }
#pragma unroll
    for (int i = 0; i < 4; i++) {
      asm volatile("cvt.rn.bf16x2.f32 %0, %1, %2;\n" : "=r"(k0[hd][i]) : "f"(acc[33 + 16 * hd + 4 * i]), "f"(acc[32 + 16 * hd + 4 * i]));
    }
  }
}
__device__ __forceinline__ void attn_own(const uint32_t (&k0)[2][4], const uint32_t (&k1)[2][4], bool le0, bool le1,
                                         const uint32_t (&qa)[2][8], float (&l)[2][4]) {
#pragma unroll
  for (int hd = 0; hd < 2; hd++) {
    float s0[4], s1[4];
    mma16816_z(s0, qa[hd][0], qa[hd][1], qa[hd][2], qa[hd][3], k0[hd][0], k0[hd][1]);
    mma16816_z(s1, qa[hd][0], qa[hd][1], qa[hd][2], qa[hd][3], k1[hd][0], k1[hd][1]);
    mma16816(s0, qa[hd][4], qa[hd][5], qa[hd][6], qa[hd][7], k0[hd][2], k0[hd][3]);
    mma16816(s1, qa[hd][4], qa[hd][5], qa[hd][6], qa[hd][7], k1[hd][2], k1[hd][3]);
    l[hd][0] = s0[0];
    l[hd][1] = s0[1];
    l[hd][2] = le0 ? s1[2] : s0[2];
    l[hd][3] = le1 ? s1[3] : s0[3];
  }
}
template <int N> __device__ __forceinline__ void quad_softmax(float (&x)[N][2], uint32_t (&pp)[N]) {
  const float c2 = 1.4426950408889634f;
  uint32_t q[N], mx[N / 2];
#pragma unroll
  for (int n = 0; n < N; n++) {
    const uint32_t r = pack_bf16(x[n][0], x[n][1]);
    q[n] = bfma2(r, 0x3e353e35u, bmul2(r, 0x379e379eu));
    x[n][0] = bf_lo(q[n]);
    x[n][1] = bf_hi(q[n]);
  }
#pragma unroll
  for (int n = 0; n < N / 2; n++)
    mx[n] = bmax2(__byte_perm(q[2 * n], q[2 * n + 1], 0x5410), __byte_perm(q[2 * n], q[2 * n + 1], 0x7632));
#pragma unroll
  for (int o = 1; o <= 2; o++)
#pragma unroll
    for (int n = 0; n < N / 2; n++) mx[n] = bmax2(mx[n], __shfl_xor_sync(0xffffffffu, mx[n], o));
  float m[N], t[N];
#pragma unroll
  for (int n = 0; n < N / 2; n++) {
    m[2 * n] = bf_lo(mx[n]);
    m[2 * n + 1] = bf_hi(mx[n]);
  }
#pragma unroll
  for (int n = 0; n < N; n++) {
    const float nm = -m[n] * c2;
    x[n][0] = ex2(fmaf(x[n][0], c2, nm));
    x[n][1] = ex2(fmaf(x[n][1], c2, nm));
    t[n] = x[n][0] + x[n][1];
  }
#pragma unroll
  for (int o = 1; o <= 2; o++)
#pragma unroll
    for (int n = 0; n < N; n++) t[n] += __shfl_xor_sync(0xffffffffu, t[n], o);
#pragma unroll
  for (int n = 0; n < N; n++) {
    const float inv = rcp(t[n]);
    pp[n] = pack_bf16(x[n][0] * inv, x[n][1] * inv);
  }
}
__device__ __forceinline__ void attn_pv(uint32_t dst, const uint32_t (&va)[4], const uint32_t (&vb)[4], uint32_t pp,
                                        uint32_t maskLE) {
  const uint32_t b0 = pp & ~maskLE, b1 = pp & maskLE;
  float oa[4], ob[4];
  mma16816_z(oa, va[0], va[1], va[2], va[3], b0, b1);
  mma16816_z(ob, vb[0], vb[1], vb[2], vb[3], b0, b1);
  stsm4t(dst, pack_bf16(oa[0], oa[1]), pack_bf16(oa[2], oa[3]), pack_bf16(ob[0], ob[1]), pack_bf16(ob[2], ob[3]));
}

template <int MODE>
__global__ void __cluster_dims__(2, 1, 1) __launch_bounds__(NTHREADS, 1)
fused_kernel(const Params p, const __grid_constant__ CUtensorMap tmX, const __grid_constant__ CUtensorMap tmW,
             const __grid_constant__ CUtensorMap tmWo,
             const __grid_constant__ CUtensorMap tmQ,
             const __grid_constant__ CUtensorMap tmXh, const __grid_constant__ CUtensorMap tmWh) {
  extern __shared__ __align__(1024) uint8_t smem[];
  const uint32_t sb = smem_u32(smem);
  const uint32_t bars = sb + OFF_BAR;
  const int tid = threadIdx.x, lane = tid & 31, warp = __shfl_sync(0xffffffffu, tid >> 5, 0);
  const int rank = blockIdx.x & 1;
  const bool halo_cta = blockIdx.x < 4;
  if (halo_cta && MODE != 0) return;
  int grp, mem;
  {
    const int t = (blockIdx.x >> 1) - 4, u = t - 32;
    const int q7 = (u * 37) >> 8;
    const bool lo = (unsigned)t < 32u, mid = (unsigned)u < 28u;
    grp = lo ? (t & 7) : (mid ? 1 + u - 7 * q7 : 0);
    mem = lo ? (t >> 3) : (mid ? 4 + q7 : (t < 0 ? t + 6 : t - 54));
  }
  const int rg = (grp >> 2) * 4 + (mem >> 1), hp = (grp & 3) * 4 + (mem & 1) * 2 + rank;
  const int rb2 = (grp >> 2) * 8 + mem, cb2 = (grp & 3) * 2 + rank;
  const int chb = grp * 16 + mem * 2 + rank;
  const int cta = rg * 16 + hp;
  const int par = rg >> 2, gidx = rg & 3;

  if (tid < 256 && !halo_cta && MODE != 2) {
    const int r = tid >> 3, c = tid & 7;
    const uint32_t so = r * 128 + ((c ^ (r & 7)) << 4);
    const __nv_bfloat16* wg0 = p.w + (size_t)r * (3 * DM) + hp * 64 + c * 8;
    const __nv_bfloat16* xg0 = p.x + (size_t)(2 * (gidx * 256 + r) + par) * DM + c * 8;
#pragma unroll
    for (int j = 0; j < 3; j++) cp_async16n(sb + OFF_1B + j * 4096 + so, wg0 + j * DM);
#pragma unroll
    for (int i = 0; i < 8; i++) cp_async16n(sb + i * 4096 + so, xg0 + (size_t)i * 64 * DM);
    asm volatile("cp.async.commit_group;\n" ::: "memory");
  }
  if (tid == 256) {
    prefetch_tmap(halo_cta ? &tmXh : &tmX);
#pragma unroll
    for (int i = 0; i < NS1B; i++) mbar_init(bars + 8 * (BAR_FULLB + i), 1);
#pragma unroll
    for (int i = 0; i < NS1A; i++) mbar_init(bars + 8 * (BAR_FULLA + i), 1);
    asm volatile("fence.mbarrier_init.release.cluster;\n" ::: "memory");
    if (!halo_cta && MODE != 2) {
      mbar_expect_tx(bars + 8 * (BAR_FULLB + 1), STG1B);
      tma_load_3d(sb + OFF_1B + 1 * STG1B, &tmW, bars + 8 * (BAR_FULLB + 1), hp * 64, 32, 0);
      mbar_expect_tx(bars + 8 * (BAR_FULLB + 2), STG1B);
      tma_load_3d(sb + OFF_1B + 2 * STG1B, &tmW, bars + 8 * (BAR_FULLB + 2), hp * 64, 64, 0);
    } else {
      prefetch_tmap(&tmWh);
    }
  } else if (tid == 288) {
#pragma unroll
    for (int i = 0; i < NS1A; i++) mbar_init(bars + 8 * (BAR_EMPTYA + i), 4);
#pragma unroll
    for (int i = 0; i < NS1B; i++) mbar_init(bars + 8 * (BAR_EMPTYB + i), 2);
    asm volatile("fence.mbarrier_init.release.cluster;\n" ::: "memory");
  } else if (tid == 320) {
#pragma unroll
    for (int i = 0; i < NS2; i++) {
      mbar_init(bars + 8 * (BAR_FULL2 + i), 1);
      mbar_init(bars + 8 * (BAR_EMPTY2 + i), 4);
    }
    mbar_init(bars + 8 * BAR_DEAD, 2);
    mbar_init(bars + 8 * (BAR_DEAD + 1), 2);
    mbar_init(bars + 8 * BAR_X, 2);
    mbar_init(bars + 8 * BAR_REL, 2);
    asm volatile("fence.mbarrier_init.release.cluster;\n" ::: "memory");
  } else if (tid == 352) {
    mbar_init(bars + 8 * BAR_T, 1);
    mbar_init(bars + 8 * BAR_UH, 3);
    mbar_init(bars + 8 * BAR_LFREE, 4);
    mbar_init(bars + 8 * BAR_LAND, 1);
    mbar_init(bars + 8 * BAR_U, 1);
    mbar_init(bars + 8 * BAR_Q, 1);
    mbar_init(bars + 8 * BAR_STG, 9);
    asm volatile("fence.mbarrier_init.release.cluster;\n" ::: "memory");
  }
  if (warp == 8) PROF2(23);
  cluster_sync_all();
  if (warp == 8) PROF2(24);

  if (warp >= 8) {
    const int hw = warp - 8;
    const int lr = lane & 7, lm = lane >> 3;
    auto g1_issue_a = [&](int j, int s) {
      const uint32_t fb = bars + 8 * (BAR_FULLA + s);
      mbar_expect_tx(fb, STG1A);
      tma_load_3d_mc(sb + s * STG1A + rank * 16384, &tmX, fb, j * 64, par, gidx * 256 + rank * 128);
    };
    auto g1_issue_b = [&](int kb, int s) {
      const uint32_t fb = bars + 8 * (BAR_FULLB + s);
      mbar_expect_tx(fb, STG1B);
      tma_load_3d(sb + OFF_1B + s * STG1B, &tmW, fb, hp * 64, kb * 32, 0);
    };
    asm volatile("setmaxnreg.dec.sync.aligned.u32 %0;\n" :: "n"(REG_HELP));

    if (halo_cta) {
      if (hw == 0) {
        int s = 0, ph = 1;
#pragma unroll 1
        for (int kb = 0; kb < 16; kb++) {
          mbar_wait(bars + 8 * (BAR_EMPTYB + s), ph);
          const uint32_t fb = bars + 8 * (BAR_FULLB + s), st = sb + s * STGH;
          if (elect_one()) {
            mbar_expect_tx(fb, STGH);
            tma_load_4d(st, &tmXh, fb, kb * 64, 248, 0, 0);
            tma_load_3d(st + 8192, &tmWh, fb, 0, kb * 64, 16 + blockIdx.x * 4);
            tma_load_3d(st + 8192 + 32768, &tmWh, fb, 0, kb * 64, 32 + blockIdx.x * 4);
          }
          if (++s == 3) { s = 0; ph ^= 1; }
        }
      }
      __syncwarp();
    } else if (hw == 0) {
      uint32_t epoch = 0;
      if (lane < (MODE == 2 ? NS2 : 2)) mbar_arrive_cluster_n(mapa(bars, rank) + 8 * (BAR_EMPTY2 + lane), 4);
      if (MODE != 2) {
      epoch = ld_relaxed(g_flag_o + 2 * cta) + 1;
      if (lane == 0) {
        mbar_expect_tx(bars + 8 * BAR_U, 32768);
        mbar_expect_tx(bars + 8 * BAR_LAND, 32768 + 64);
        mbar_expect_tx(bars + 8 * BAR_Q, 32768);
        mbar_expect_tx(bars + 8 * BAR_T, T_END);
      }
      {
        int sa = 1, pha = 1, sbb = 2, phb = 1;
#pragma unroll 1
        for (int kb = 2; kb < 32; kb++) {
          if (!(kb & 1)) {
            mbar_wait(bars + 8 * (BAR_EMPTYA + sa), pha);
            if (elect_one()) g1_issue_a(kb >> 1, sa);
            if (++sa == NS1A) { sa = 0; pha ^= 1; }
          }
          mbar_wait(bars + 8 * (BAR_EMPTYB + sbb), phb);
          if (kb > 2 && elect_one()) g1_issue_b(kb, sbb);
          __syncwarp();
          if (kb >= PF0 && kb < PF0 + 12)
            prefetch_l2((kb < PF0 + 8 ? p.q + (size_t)chb * 16384 + (kb - PF0) * 2048 : p.wo + (size_t)chb * 8192 + (kb - PF0 - 8) * 2048) + lane * 64);
          if (kb == 4) PROF2(27);
          if (kb == 1) PROF2(38);
          if (kb == 2) PROF2(39);
          if (++sbb == NS1B) { sbb = 0; phb ^= 1; }
        }
      }
      static_assert(32 % NS1B == 2 && (32 / NS1B) % 2 == 0 && OFF_Q == OFF_1B && 2 * STG1B == 6 * 4096, "slots / parity of these loads");
      const uint8_t* tab = reinterpret_cast<const uint8_t*>(g_tab);
      if (lane == 0) {
        prefetch_tmap(&tmWo);
        prefetch_tmap(&tmQ);
        bulk_load(sb + OFF_T + T_A1, tab + T_A1, T_END - T_A1, bars + 8 * BAR_T);
        mbar_wait(bars + 8 * (BAR_EMPTYB + 2), 1);
        tma_load_5d(sb + OFF_Q + 6 * 4096, &tmQ, bars + 8 * BAR_Q, (chb & ~1) * 8, rank * 32 + 24);
        tma_load_5d(sb + OFF_Q + 7 * 4096, &tmQ, bars + 8 * BAR_Q, (chb & ~1) * 8, rank * 32 + 28);
        if (gidx != 0) wait_flag(g_flag_h + (hp >> 2), epoch);
      }
      __syncwarp();
      {
        uint4 hk0 = make_uint4(0, 0, 0, 0), hk1 = hk0, hv0 = hk0, hv1 = hk0;
        if (gidx != 0) {
          const uint4* src = g_halo + cta * 128 + lane;
          hk0 = __ldcg(src); hk1 = __ldcg(src + 32); hv0 = __ldcg(src + 64); hv1 = __ldcg(src + 96);
        }
        if (lane == 0) {
          mbar_wait(bars + 8 * (BAR_EMPTYB + 3), 1);
          bulk_load(sb + OFF_T, tab, T_TW, bars + 8 * BAR_T);
        }
        __syncwarp();
        PROF2(18);
        sts128(sb + OFF_L0 + 1024 + lane * 16, hk0.x, hk0.y, hk0.z, hk0.w);
        sts128(sb + OFF_L0 + 1536 + lane * 16, hk1.x, hk1.y, hk1.z, hk1.w);
        stsm4(sb + OFF_L0 + lr * 128 + ((lm ^ lr) << 4), hv0.x, hv0.y, hv0.z, hv0.w);
        stsm4(sb + OFF_L0 + lr * 128 + (((4 + lm) ^ lr) << 4), hv1.x, hv1.y, hv1.z, hv1.w);
        __syncwarp();
        if (lane == 0) {
          mbar_arrive(bars + 8 * BAR_STG);
          mbar_wait(bars + 8 * (BAR_EMPTYB + 4), 1);
          bulk_load(sb + OFF_T + T_TW, tab + T_TW, T_A1 - T_TW, bars + 8 * BAR_T);
          mbar_wait(bars + 8 * BAR_EMPTYB, 0);
#pragma unroll 1
          for (int i = 0; i < 6; i++) tma_load_5d(sb + OFF_Q + i * 4096, &tmQ, bars + 8 * BAR_Q, (chb & ~1) * 8, rank * 32 + i * 4);
        }
        __syncwarp();
      }
      }
      if (MODE != 1) {
        auto korder = [&](int i) { return MODE == 2 ? i : g2_k(hp, i); };
        const __nv_bfloat16* osrc = g_o + (size_t)(rb2 >> 1) * 16 * 16384 + ((rb2 & 1) * 2 + rank) * 4096;
        const uint32_t* flag = g_flag_o + (rb2 >> 1) * 32 + korder(lane & 15) * 2 + (rb2 & 1);
        uint32_t ready = MODE == 0 ? 0u : ~0u, pv = 0;
        auto look = [&]() {
          ready |= __ballot_sync(0xffffffffu, pv == epoch);
          asm volatile("fence.acquire.gpu;\n" ::: "memory");
          fence_async_all();
        };
        if (MODE == 0) {
          mbar_wait_idle(bars + 8 * BAR_REL, 0);
          if (POLL1) pv = ld_relaxed(flag);
          if (elect_one()) {
            mbar_expect_tx(bars + 8 * BAR_FULL2, STG2);
            tma_load_3d(sb + g2_b(0), &tmWo, bars + 8 * BAR_FULL2, 0, korder(0) * 64, cb2 * 2);
            tma_load_3d(sb + g2_b(1), &tmWo, bars + 8 * (BAR_FULL2 + 1), 0, korder(1) * 64, cb2 * 2);
          }
          if (POLL1) look();
        }
#pragma unroll
        for (int i = MODE == 0 ? 2 : 0; i < 16; i++) {
          const int kb = korder(i), s = i % NS2, ph = (i / NS2) & 1;
          const uint32_t fb = bars + 8 * (BAR_FULL2 + s);
          if (!((ready >> i) & 1)) {
            int n = 0;
            do {
              ready |= __ballot_sync(0xffffffffu, ld_acquire(flag) == epoch);
            } while (!((ready >> i) & 1) && ++n < SPIN_LIMIT);
            fence_async_all();
          }
          if (i == 2) PROF(21);
          mbar_wait(bars + 8 * (BAR_EMPTY2 + s), ph);
          if (elect_one()) {
            mbar_expect_tx(fb, STG2);
            asm volatile(
                "cp.async.bulk.shared::cluster.global.mbarrier::complete_tx::bytes.multicast::cluster [%0], [%1], %2, [%3], %4;\n"
                ::"r"(sb + g2_a(s) + rank * 8192), "l"(osrc + kb * 16384), "r"(8192), "r"(fb), "h"((uint16_t)3) : "memory");
            if (MODE != 0 || i >= 4) tma_load_3d(sb + g2_b(s), &tmWo, fb, 0, kb * 64, cb2 * 2);
          }
          if (MODE == 0 && i == LA0) pv = ld_relaxed(flag);
          if (MODE == 0 && i == LA1) look();
          if (i == 3) PROF(37);

        }
      }
      __syncwarp();
    } else if (MODE != 2) {
      {
        const int g = lane >> 2, t = lane & 3;
        uint32_t w[2][4];
#pragma unroll
        for (int h = 0; h < 2; h++) {
          const uint2 x = __ldg(reinterpret_cast<const uint2*>(p.shift_k + ((chb & ~1) * 8 + h * 8 + g) * 4));
          w[h][0] = __byte_perm(x.x, x.x, 0x1010);
          w[h][1] = __byte_perm(x.x, x.x, 0x3232);
          w[h][2] = __byte_perm(x.y, x.y, 0x1010);
          w[h][3] = __byte_perm(x.y, x.y, 0x3232);
        }
        auto swz = [](int r) { return (((r & 29) | ((r ^ (r >> 2)) & 2)) << 5) | (r & 16); };
        const uint32_t kring = sb + OFF_H + (hw - 1) * 8192, vring = kring + 4096;
        const int s0 = rank * 32 + (hw - 1) * 11, s1 = hw == 3 ? rank * 32 + 32 : s0 + 11;
        const size_t goff = (size_t)(lane >> 1) * DM + (chb & ~1) * 8 + (lane & 1) * 8;
        const __nv_bfloat16* kg = p.k + goff;
        const __nv_bfloat16* vg = p.v + goff;
        const uint32_t d0 = swz(lane >> 1) ^ ((lane & 1) << 4), d1 = swz(16 + (lane >> 1)) ^ ((lane & 1) << 4);
        auto issue = [&](int st) {
          const uint32_t so = (st & 3) << 10;
          cp_async16(kring + so + d0, kg + (size_t)st * 32 * DM, 16);
          cp_async16(kring + so + d1, kg + (size_t)(st * 32 + 16) * DM, 16);
          cp_async16(vring + so + d0, vg + (size_t)st * 32 * DM, 16);
          cp_async16(vring + so + d1, vg + (size_t)(st * 32 + 16) * DM, 16);
        };
        const int xa = 8 * (lr >> 1) + 2 * lm + (lr & 1), xb = 8 * (lr >> 1) - 4 + 2 * (lm & 1) + (lr & 1);
        const uint32_t la = swz(xa), lb = swz(xb & 31);
        const int backb = xb < 0 ? 1 : 0;
        const uint32_t ud[2] = {mapa(sb + OFF_U + g * 4096 + t * 16, 0), mapa(sb + OFF_U + g * 4096 + t * 16, 1)};
        const uint32_t ub[2] = {mapa(bars + 8 * BAR_U, 0), mapa(bars + 8 * BAR_U, 1)};
        if (lane == 0) mbar_wait(bars + 8 * (BAR_FULLB + NS1B - 1), 0);
        __syncwarp();
        if (lane >= 24) cp_async16(kring + (((s0 - 1) & 3) << 10) + d1, s0 > 0 ? kg + (size_t)(s0 * 32 - 16) * DM : kg, s0 > 0 ? 16 : 0);
        issue(s0);
        asm volatile("cp.async.commit_group;\n" ::: "memory");
        issue(s0 + 1);
        asm volatile("cp.async.commit_group;\n" ::: "memory");
#pragma unroll 1
        for (int st = s0; st < s1; st++) {
          if (st + 2 < s1) issue(st + 2);
          if (hw == 1 && st - s0 < 8) prefetch_l2(p.ssm_k + (size_t)(chb * 8 + st - s0) * SEQ + lane * 64);
          if (hw == 2 && st == s0 + 4 && lane < 2) prefetch_l2(g_tab + (chb * 2 + lane) * 32);
          const uint32_t uo = (st ^ ((g ^ (st >> 2)) & 1)) * 64;
          asm volatile("cp.async.commit_group;\n" ::: "memory");
          asm volatile("cp.async.wait_group 2;\n" ::: "memory");
          __syncwarp();
#pragma unroll
          for (int h = 0; h < 2; h++) {
            uint32_t e[6], vv[4], e4[4];
            ldsm4t(e4, kring + ((st & 3) << 10) + (la ^ (h << 4)));
            ldsm2t(e[0], e[1], kring + (((st - backb) & 3) << 10) + (lb ^ (h << 4)));
            ldsm4t(vv, vring + ((st & 3) << 10) + (la ^ (h << 4)));
            e[2] = e4[0]; e[3] = e4[1]; e[4] = e4[2]; e[5] = e4[3];
            uint32_t o[5];
#pragma unroll
            for (int i = 0; i < 5; i++) o[i] = __byte_perm(e[i], e[i + 1], 0x5432);
#pragma unroll
            for (int i = 0; i < 4; i++) {
              uint32_t a = bmul2(o[i], w[h][3]);
              a = bfma2(e[i + 1], w[h][2], a);
              a = bfma2(o[i + 1], w[h][1], a);
              a = bfma2(e[i + 2], w[h][0], a);
              vv[i] = bmul2(a, vv[i]);
            }
            st_async128(ud[h] + uo, ub[h], vv[0], vv[1], vv[2], vv[3]);
          }
          __syncwarp();
        }
        PROF(16);
      }
      {
        const int rw = (lane >> 3) + (lane & 4), ck = lane & 3;
        const uint32_t so = rw * 64 + ck * 16, dof = rw * 128 + ((ck ^ rw) << 4);
        const uint8_t* hsrc = reinterpret_cast<const uint8_t*>(p.ssm_k + (size_t)chb * 8 * SEQ) + so;
        const float dv = lane < 8 ? __bfloat162float(p.ssm_D[chb * 8 + lane]) : 0.f;
        uint32_t x[32];
        auto load = [&](const uint8_t* src, int i) {
          asm volatile("ld.v4.u32 {%0,%1,%2,%3}, [%4];\n" : "=r"(x[4 * i]), "=r"(x[4 * i + 1]), "=r"(x[4 * i + 2]), "=r"(x[4 * i + 3])
                       : "l"(src + i * 512) : "memory");
        };
#pragma unroll
        for (int i = 0; i < 8; i++) load(hsrc + (hw - 1) * 4096, i);
        nb_sync(NB_HELP3, 96);
        mbar_wait(bars + 8 * BAR_U, 0);
        int eh = 0;
#pragma unroll 1
        for (int n = 2 * (hw - 1); n < 16; n += (n & 1) ? 5 : 1) {
          const int c = n >> 1;
          const uint8_t* nsrc = (n & 1) ? hsrc + (c < 5 ? c + 3 : c) * 4096
                                        : smem + OFF_U + c * 4096 + (so ^ (((c ^ (lane >> 2)) & 1) << 6));
          const uint32_t dst = sb + ((n & 1) ? OFF_U : OFF_H) + c * 4096 + dof;
          const float dc = __shfl_sync(0xffffffffu, dv, c);
          const float h0 = bf_lo(x[0]) + ((lane | (n & 1)) == 0 ? dc : 0.f), h1 = bf_hi(x[0]);
          x[0] = pack_bf16(h0, h1);
          uint32_t m[2] = {x[0], x[1]};
#pragma unroll
          for (int i = 2; i < 32; i++) asm("max.xorsign.abs.bf16x2 %0, %0, %1;\n" : "+r"(m[i & 1]) : "r"(x[i]));
          asm("max.xorsign.abs.bf16x2 %0, %0, %1;\n" : "+r"(m[0]) : "r"(m[1]));
          const uint32_t e = max(__reduce_max_sync(0xffffffffu, max((m[0] >> 7) & 255u, (m[0] >> 23) & 255u)), 5u);
          const uint32_t sc = (259u - e) * 0x00800080u;
#pragma unroll
          for (int i = 0; i < 8; i++) {
            uint32_t o[4];
#pragma unroll
            for (int j = 0; j < 4; j++) {
              const uint32_t v = bmul2(x[4 * i + j], sc);
              asm("cvt.rn.f16x2.f32 %0, %1, %2;\n" : "=r"(o[j]) : "f"(bf_hi(v)), "f"(i + j == 0 ? h0 * bf_hi(sc) : bf_lo(v)));
            }
            sts128((dst + (i & 3) * 1024) ^ ((i >> 2) << 6), o[0], o[1], o[2], o[3]);
            load(nsrc, i);
          }
          if (n & 1) {
            const int f = min(max((int)e + eh - 129, 0), 254);
            if (lane < 2)
              asm volatile("st.async.weak.shared::cluster.mbarrier::complete_tx::bytes.b32 [%0], %2, [%1];\n"
                           ::"r"(mapa(sb + OFF_SC + rank * 32 + c * 4, lane)), "r"(mapa(bars + 8 * BAR_LAND, lane)), "r"(f << 7) : "memory");
          }
          eh = e;
        }
        fence_async_smem();
        __syncwarp();
        if (lane == 0) mbar_arrive(bars + 8 * BAR_UH);
        PROF(32);
      }
      if (hw < 3) {
        const uint32_t rb = mapa(bars, lane & 1);
        const uint32_t epoch = ld_relaxed(g_flag_o + 2 * cta + hw - 1) + 1;
        const bool own = hw - 1 == (rb2 & 1);
        nb_sync(NB_OREADY + hw - 1, 160);
        if (lane == 0) {
          asm volatile("cp.async.bulk.global.shared::cta.bulk_group [%0], [%1], %2;\n" ::"l"(g_o + (size_t)cta * 16384 + (hw - 1) * 8192),
                       "r"(sb + OFF_OP + (own ? 16384 : 0)), "r"(16384) : "memory");
          bulk_commit();
        }
        if (lane < 2) {
          mbar_arrive_cluster(rb + 8 * (BAR_EMPTY2 + 2));
          mbar_arrive_cluster(rb + 8 * (BAR_EMPTY2 + 3));
        }
        if (lane == 0) {
          bulk_wait0();
          if (own) mbar_expect_tx(bars + 8 * (BAR_FULL2 + 1), 16384);
          mbar_arrive_cluster(mapa(bars, own ? rank : rank ^ 1) + 8 * BAR_X);
          st_release(g_flag_o + 2 * cta + hw - 1, epoch);
          mbar_arrive(bars + 8 * BAR_REL);
        }
        __syncwarp();
        PROF(own ? 17 : 19);
      } else {
        if (MODE == 0) {
          mbar_wait_idle(bars + 8 * BAR_X, 0);
          if (elect_one())
            asm volatile("cp.async.bulk.shared::cluster.shared::cta.mbarrier::complete_tx::bytes [%0], [%1], %2, [%3];\n"
                         ::"r"(mapa(sb + OFF_OP, rank ^ 1)), "r"(sb + OFF_OP + 16384), "r"(16384),
                         "r"(mapa(bars + 8 * BAR_FULL2, rank ^ 1)) : "memory");
        }
        if (MODE == 0) {
          mbar_wait_idle(bars + 8 * BAR_DEAD, 0);
          if (elect_one()) {
            tma_load_3d(sb + g2_b(2), &tmWo, bars + 8 * (BAR_FULL2 + 2), 0, g2_k(hp, 2) * 64, cb2 * 2);
            tma_load_3d(sb + g2_b(3), &tmWo, bars + 8 * (BAR_FULL2 + 3), 0, g2_k(hp, 3) * 64, cb2 * 2);
          }
        }
        __syncwarp();
      }
      {
        const int c8 = (4 * (lr >> 1) + 2 * (lm & 1) + (lr & 1)) & 7;
        const bool own = (lr >> 2) == rank;
        const uint32_t ya = sb + (own ? y_slot(c8 & 1, c8 >> 1) : OFF_LAND + c8 * 2048);
        const uint32_t yx = ((lm >> 1) ^ lr) << 4;
        const int row = (lane >> 4) * 8 + ((lane >> 3) & 1) * 16 + ((lane >> 2) & 1);
        uint2* og = reinterpret_cast<uint2*>(p.out + (size_t)(rank * 1024 + row) * (2 * DM) + (chb & ~1) * 8 + (lane & 3) * 4);
        const uint32_t qa = sb + OFF_Q + (lane >> 4) * 512 + (lane & 15) * 8;
        mbar_wait(bars + 8 * BAR_Q, 0);
        mbar_wait_idle(bars + 8 * BAR_LAND, 0);
        PROF(33);
        const uint32_t t0 = clock();
        const uint4 s4 = lds128(sb + OFF_SC + (lane & 3) * 16);
        const uint32_t sc[2] = {s4.x | (s4.y << 16), s4.z | (s4.w << 16)};
        auto fin = [&](uint32_t q2, uint32_t y2, uint32_t s2) {
          float lo, hi;
          asm("{\n.reg .b16 l, h;\nmov.b32 {l, h}, %2;\ncvt.f32.f16 %0, l;\ncvt.f32.f16 %1, h;\n}\n" : "=f"(lo), "=f"(hi) : "r"(y2));
          return bmul2(q2, bmul2(pack_bf16(lo, hi), s2));
        };
#pragma unroll 1
        for (int j = hw - 1; j < 16; j += 3) {
          uint32_t y[4][4];
          uint2 q[8];
          while ((uint32_t)clock() - t0 < j * PACE) __nanosleep(40);
          const uint32_t qj = qa + j * 2048;
#pragma unroll
          for (int i = 0; i < 4; i++) ldsm4t(y[i], ya + j * 128 + (yx ^ (i << 5)));
#pragma unroll
          for (int i = 0; i < 8; i++) q[i] = lds64(qj + (i >> 2) * 1024 + (i & 3) * 128);
#pragma unroll
          for (int i = 0; i < 8; i++) {
            og[(size_t)(j * 64 + (i >> 2) * 32 + (i & 3) * 2) * (2 * DM / 4)] =
                make_uint2(fin(q[i].x, y[i >> 1][2 * (i & 1)], sc[0]), fin(q[i].y, y[i >> 1][2 * (i & 1) + 1], sc[1]));
            if (i < 7) asm volatile("nanosleep.u32 %0;\n" ::"r"(FINE) : "memory");
          }
        }
      }
      PROF(22);
    }
    cluster_sync_all();
  } else {
    asm volatile("setmaxnreg.inc.sync.aligned.u32 %0;\n" :: "n"(REG_MATH));
    if (warp == 0) PROF2(26);
    const int wg = warp >> 2;
    const int wtid = tid & 127;
    const bool signaller = (wtid == 0) || (wtid == 32);
    const uint32_t rbars = mapa(bars, wtid >> 5 & 1);

    if (halo_cta) {
      const uint32_t epoch = ld_relaxed(g_flag_h + blockIdx.x) + 1;
      float acc0[64], acc1[64];
      int s = 0, ph = 0;
#pragma unroll 1
      for (int kb = 0; kb < 16; kb++) {
        mbar_wait(bars + 8 * (BAR_FULLB + s), ph);
        const uint32_t st = sb + s * STGH;
        const uint64_t da = mkdesc(st, 16, 1024, 1);
        const uint64_t db = mkdesc(st + 8192 + wg * 32768, 8192, 1024, 1);
        wg_fence();
#pragma unroll
        for (int kk = 0; kk < 4; kk++) {
          wgmma_n128(acc0, da + 2 * kk, db + 128 * kk, kb + kk);
          wgmma_n128(acc1, da + 2 * kk, db + 1024 + 128 * kk, kb + kk);
        }
        wg_commit();
        wg_wait<0>();
        if (wtid == 0) mbar_arrive(bars + 8 * (BAR_EMPTYB + s));
        if (++s == 3) { s = 0; ph ^= 1; }
      }
      fence_regs(acc0);
      fence_regs(acc1);
      if ((warp & 3) != 3) {
#pragma unroll
        for (int hh = 0; hh < 2; hh++) {
          uint4* dst = g_halo + ((hh * 4 + (warp & 3) + 1) * 16 + blockIdx.x * 4) * 128 + wg * 64 + lane;
#pragma unroll
          for (int j = 0; j < 4; j++) {
            const int o = 16 * j + 2 * hh;
            dst[(j >> 1) * 128 + (j & 1) * 32] =
                make_uint4(pack_bf16(acc0[o], acc0[o + 1]), pack_bf16(acc0[o + 4], acc0[o + 5]),
                           pack_bf16(acc0[o + 8], acc0[o + 9]), pack_bf16(acc0[o + 12], acc0[o + 13]));
            dst[(2 + (j >> 1)) * 128 + (j & 1) * 32] =
                make_uint4(pack_bf16(acc1[o], acc1[o + 1]), pack_bf16(acc1[o + 4], acc1[o + 5]),
                           pack_bf16(acc1[o + 8], acc1[o + 9]), pack_bf16(acc1[o + 12], acc1[o + 13]));
          }
        }
      }
      nb_sync(NB_G1DONE, 256);
      if (tid == 0) st_release(g_flag_h + blockIdx.x, epoch);
      PROF(36);
      cluster_sync_all();
      return;
    }

    float acc[64];
    auto g2_step = [&](int s, int kb) {
      const uint64_t da = mkdesc(sb + g2_a(s) + wg * 8192, 16, 1024, 1);
      const uint64_t db = mkdesc(sb + g2_b(s), 8192, 1024, 1);
      wg_fence();
      wgmma_n128(acc, da, db, kb);
      wgmma_n128(acc, da + 2, db + 128, 1);
      wgmma_n128(acc, da + 4, db + 256, 1);
      wgmma_n128(acc, da + 6, db + 384, 1);
      wg_commit();
    };

    if (MODE != 2) {
    uint32_t a1[2][4], tw[16], d1[32];
    const uint32_t tb = sb + OFF_T + wtid * 16;
    const uint64_t dx = mkdesc(sb + OFF_U + wg * 4096, OFF_H - OFF_U, 1024, 1);
    auto s1 = [&](int it) {
      hmma_n128t<0>(d1, a1[0], dx + it * 512);
      hmma_n128t<1>(d1, a1[1], dx + it * 512 + 128);
      wg_commit();
    };
    auto ldtw = [&](int i) {
      const uint4 v = lds128(tb + T_TW + i * 2048);
      tw[4 * i] = v.x; tw[4 * i + 1] = v.y; tw[4 * i + 2] = v.z; tw[4 * i + 3] = v.w;
    };
    {
      float acc0[96], acc1[96];
      int sa = 0, pha = 0, sbb = 0, phb = 0;
      asm volatile("cp.async.wait_group 0;\n" ::: "memory");
      fence_async_smem();
      nb_sync(NB_FIRST, 256);
      if (tid == 0) {
        mbar_arrive(bars + 8 * BAR_FULLA);
        mbar_arrive(bars + 8 * BAR_FULLB);
      }
      PROF(0 + wg);
#pragma unroll 1
      for (int kb = 0; kb < 30; kb++) {
        if (!(kb & 1)) mbar_wait(bars + 8 * (BAR_FULLA + sa), pha);
        mbar_wait(bars + 8 * (BAR_FULLB + sbb), phb);
        if (kb == 0) PROF2(0 + wg);
        if (kb == 4 && wg == 0) PROF2(28);
        if (kb == 8 && wg == 0) PROF2(29);
        if (kb == 16 && wg == 0) PROF2(30);
        const uint64_t da = mkdesc(sb + sa * STG1A + wg * 16384 + (kb & 1) * 64, 16, 1024, 1);
        const uint64_t db = mkdesc(sb + OFF_1B + sbb * STG1B, 4096, 1024, 1);
        wg_fence();
        wgmma_n192(acc0, da, db, kb);
        wgmma_n192(acc1, da + 512, db, kb);
        wgmma_n192(acc0, da + 2, db + 128, 1);
        wgmma_n192(acc1, da + 514, db + 128, 1);
        wg_commit();
        wg_wait<1>();
        if (kb > 0) {
          if (wtid == 64) mbar_arrive(bars + 8 * (BAR_EMPTYB + (sbb == 0 ? NS1B - 1 : sbb - 1)));
          if (!(kb & 1) && signaller) mbar_arrive_cluster(rbars + 8 * (BAR_EMPTYA + (sa == 0 ? NS1A - 1 : sa - 1)));
        }
        if (++sbb == NS1B) { sbb = 0; phb ^= 1; }
        if ((kb & 1) && ++sa == NS1A) { sa = 0; pha ^= 1; }
      }
      const int blk0 = wg * 8 + (warp & 3);
      const int lr = lane & 7, lm = lane >> 3;
      const bool le0 = 2 * (lane & 3) <= (lane >> 2), le1 = 2 * (lane & 3) + 1 <= (lane >> 2);
      const uint32_t maskLE = (le0 ? 0x0000FFFFu : 0u) | (le1 ? 0xFFFF0000u : 0u);
      uint32_t k0[2][2][4], k1[2][2][4], qa[2][2][8];
      float l[2][2][4];
      {
        static_assert(15 % NS1A == 0 && 30 % NS1B == 0, "slots of the last k blocks");
        mbar_wait(bars + 8 * BAR_FULLA, 1);
        mbar_wait(bars + 8 * BAR_FULLB, 0);
        mbar_wait(bars + 8 * (BAR_FULLB + 1), 0);
        const uint64_t da = mkdesc(sb + wg * 16384, 16, 1024, 1);
        const uint64_t db = mkdesc(sb + OFF_1B, 4096, 1024, 1);
        wg_fence();
#pragma unroll
        for (int i = 0; i < 4; i++) wgmma_n192(acc0, da + 2 * i, db + (i >> 1) * (STG1B >> 4) + (i & 1) * 128, 1);
        wg_commit();
        wg_wait<1>();
        if (wtid == 64) mbar_arrive(bars + 8 * (BAR_EMPTYB + NS1B - 1));
#pragma unroll
        for (int i = 0; i < 2; i++) wgmma_n192(acc1, da + 512 + 2 * i, db + (i >> 1) * (STG1B >> 4) + (i & 1) * 128, 1);
        wg_commit();
        wg_wait<1>();
        fence_regs(acc0);
        attn_stage(sb, blk0, lane, acc0, k1[0]);
#pragma unroll
        for (int i = 2; i < 4; i++) wgmma_n192(acc1, da + 512 + 2 * i, db + (i >> 1) * (STG1B >> 4) + (i & 1) * 128, 1);
        wg_commit();
        attn_pack(acc0, qa[0], k0[0]);
        wg_wait<0>();
        fence_regs(acc1);
      }
      if (wtid == 64) mbar_arrive(bars + 8 * BAR_EMPTYB);
      PROF(2 + wg);
      attn_stage(sb, blk0 + 4, lane, acc1, k1[1]);
      __syncwarp();
      if (lane == 0) mbar_arrive(bars + 8 * BAR_STG);
      mbar_wait(bars + 8 * BAR_U, 0);
      attn_pack(acc1, qa[1], k0[1]);
      attn_own(k0[0], k1[0], le0, le1, qa[0], l[0]);
      attn_own(k0[1], k1[1], le0, le1, qa[1], l[1]);
      const uint32_t cho[2] = {(uint32_t)(((lm & 1) ^ lr) << 4), (uint32_t)(((2 + (lm & 1)) ^ lr) << 4)};
      const uint32_t obase = sb + OFF_OP + (wg == (rb2 & 1) ? 16384 : 0) + ((warp & 3) * 16 + lr) * 128;
      mbar_wait(bars + 8 * BAR_STG, 0);
      {
        uint32_t km[4][4], va[8][4], vb[8][4], pp[8];
        float x[8][2];
#pragma unroll
        for (int n = 0; n < 4; n++) {
          const int blk = blk0 + 4 * (n >> 1);
          to_arr(km[n], lds128(sb + (blk == 0 ? OFF_L0 + 1024 : OFF_KH + (blk - 1) * 2048) + (n & 1) * 512 + lane * 16));
        }
#pragma unroll
        for (int n = 0; n < 8; n++) {
          const int vr = (blk0 + 4 * ((n >> 1) & 1)) * 16 - 8 + 8 * (n >> 2) + 8 * (lm >> 1);
          const uint32_t vrow = sb + (vr < 0 ? OFF_L0 : OFF_VP + vr * 128) + lr * 128;
          ldsm4t(va[n], vrow + (cho[0] ^ ((n & 1) << 6)));
          ldsm4t(vb[n], vrow + (cho[1] ^ ((n & 1) << 6)));
        }
        const bool first = blk0 == 0 && gidx == 0;
#pragma unroll
        for (int n = 0; n < 4; n++) {
          const uint32_t(&q)[8] = qa[n >> 1][n & 1];
          float sm[4];
          mma16816_z(sm, q[0], q[1], q[2], q[3], km[n][0], km[n][1]);
          mma16816(sm, q[4], q[5], q[6], q[7], km[n][2], km[n][3]);
          if (n < 2 && first) sm[0] = sm[1] = -1e9f / 0.17677669529663687f;
          x[n][0] = le0 ? l[n >> 1][n & 1][0] : sm[0];
          x[n][1] = le1 ? l[n >> 1][n & 1][1] : sm[1];
          x[4 + n][0] = l[n >> 1][n & 1][2];
          x[4 + n][1] = l[n >> 1][n & 1][3];
        }
        quad_softmax<8>(x, pp);
#pragma unroll
        for (int n = 7; n >= 0; n--)
          attn_pv(obase + ((n >> 1) & 1) * 8192 + (n >> 2) * 1024 + (((4 * (n & 1) + lm) ^ lr) << 4), va[n], vb[n], pp[n],
                  maskLE);
      }
      fence_async_smem();
      nb_arrive(NB_OREADY + wg, 160);
    }

    {
      const int w = warp & 3;
      uint32_t a4[8][4];
      uint32_t d4[8];
      PROF(34 + wg);
      const uint64_t dz = mkdesc(sb + OFF_U + wg * 4096, 512, 128, 0);
      const uint64_t db2 = mkdesc(sb + OFF_T + T_B2, 128, 256, 0);
      mbar_wait(bars + 8 * BAR_T, 0);
      mbar_wait(bars + 8 * BAR_UH, 0);
      to_arr(a1[0], lds128(tb + T_A1));
      to_arr(a1[1], lds128(tb + T_A1 + 2048));
      wg_fence();
      s1(0);
      ldtw(0);
      ldtw(1);
      const uint32_t za = sb + (w < 2 ? OFF_U : OFF_H) + wg * 4096 + (w & 1) * 2048 + lane * 16;
      const uint32_t yl = (wtid ^ (4 * rank + wg)) * 16;
      const uint32_t yown = mapa(sb, rank) + yl, yrem = mapa(sb + OFF_LAND + wg * 2048, rank ^ 1) + yl;
      const uint32_t yb[2] = {mapa(bars + 8 * BAR_LAND, 0), mapa(bars + 8 * BAR_LAND, 1)};
      wg_wait<0>();
      fence_regs(d1);
      nb_sync(NB_WG + wg, 128);
      auto s4 = [&](int it) {
        wg_fence();
#pragma unroll
        for (int ks = 0; ks < 8; ks++) {
          const uint64_t d = dz + (it & 1) * 512 + (ks & 3) * 64 + (ks >> 2) * ((OFF_H - OFF_U) >> 4);
          if (ks == 0) hmma_n32<0, 1>(d4, a4[ks], d);
          else hmma_n32<1, 1>(d4, a4[ks], d);
        }
        wg_commit();
      };
      auto e4 = [&](int it) {
        fence_regs(d4);
        const uint32_t o = (yown + y_slot(wg, it)) ^ ((it >> 1) << 5), m = (yrem + it * 4096) ^ ((it >> 1) << 5);
        if (it == 0) mbar_wait(bars + 8 * BAR_LFREE, 0);
        if (it == 3) mbar_wait(bars + 8 * (BAR_DEAD + 1), 0);
        st_async128(rank ? m : o, yb[0], d4[0], d4[1], d4[2], d4[3]);
        st_async128(rank ? o : m, yb[1], d4[4], d4[5], d4[6], d4[7]);
      };
      uint32_t a2[2][2][2][4], a3[2][2][4], d2[2][2][8], d3[2][8];
      auto s2a = [&]() {
        wg_fence();
#pragma unroll
        for (int c = 0; c < 4; c++) hmma_n32<0, 0>(d2[c & 1][c >> 1], a2[0][c & 1][c >> 1], db2 + (c >> 1) * 128);
      };
      auto s2b = [&]() {
        wg_fence();
#pragma unroll
        for (int c = 0; c < 4; c++) {
          hmma_n32<1, 0>(d2[c & 1][c >> 1], a2[1][c & 1][c >> 1], db2 + (c >> 1) * 128 + 64);
          if (c & 1) wg_commit();
        }
      };
      auto done = [&](int it) {
        if (it == 0) {
          if (signaller) mbar_arrive_cluster(rbars + 8 * BAR_LFREE);
        } else if (it >= 2 && wtid == 64) {
          mbar_arrive(bars + 8 * (BAR_DEAD + it - 2));
        }
        if (w == 0) PROF3(40 + 4 * wg + it);
      };
      fft_e1<0>(d1, tw, a2[0]);
      s2a();
      fft_e1<1>(d1, tw, a2[1]);
      s2b();
      s1(1);
      ldtw(2);
      ldtw(3);
#pragma unroll
      for (int i = 0; i < 8; i++) to_arr(a4[i], lds128(tb + T_A4 + i * 2048));
#pragma unroll
      for (int it = 0; it < 4; it++) {
        if (it == 0 || it == 3) wg_wait<2>(); else wg_wait<3>();
        fence_regs(d2[0][0]);
        fence_regs(d2[1][0]);
        fft_e2<0, 0>(d2[0][0], d2[1][0], a3[0]);
        fft_e2<0, 1>(d2[0][0], d2[1][0], a3[1]);
        if (it == 0 || it == 3) wg_wait<1>(); else wg_wait<2>();
        fence_regs(d2[0][1]);
        fence_regs(d2[1][1]);
        fft_e2<1, 0>(d2[0][1], d2[1][1], a3[0]);
        fft_e2<1, 1>(d2[0][1], d2[1][1], a3[1]);
        wg_fence();
        hmma_n32<0, 0>(d3[0], a3[0][0], db2);
        hmma_n32<0, 0>(d3[1], a3[0][1], db2);
        hmma_n32<1, 0>(d3[0], a3[1][0], db2 + 64);
        hmma_n32<1, 0>(d3[1], a3[1][1], db2 + 64);
        wg_commit();
        wg_wait<1>();
        if (it > 0) e4(it - 1);
        if (it < 3) {
          fence_regs(d1);
          fft_e1<0>(d1, tw, a2[0]);
        }
        wg_wait<0>();
        fence_regs(d3[0]);
        fence_regs(d3[1]);
        if (it < 3) s2a();
        fft_e3(d3, tw, za + (it & 1) * 8192);
        if (it < 3) {
          fft_e1<1>(d1, tw, a2[1]);
          s2b();
        }
        fence_async_smem();
        nb_sync(NB_WG + wg, 128);
        done(it);
        s4(it);
        if (it < 2) s1(it + 2);
      }
      if (PEEL && MODE == 0) {
        mbar_wait(bars + 8 * BAR_FULL2, 0);
        g2_step(0, 0);
        wg_wait<1>();
      } else {
        wg_wait<0>();
      }
      if (signaller) mbar_arrive_cluster(rbars + 8 * (BAR_EMPTY2 + 4));
      e4(3);
      if (PEEL && MODE == 0) {
        wg_wait<0>();
        if (signaller) mbar_arrive_cluster(rbars + 8 * BAR_EMPTY2);
      }
      PROF(6 + wg);
    }
    }

    if (MODE != 1) {
      int s = PEEL && MODE == 0, ph = 0;
#pragma unroll 1
      for (int kb = s; kb < STAG; kb++) {
        mbar_wait(bars + 8 * (BAR_FULL2 + s), ph);
        if (kb == 1) PROF(8 + wg);
        if (warp == 4) PROF2(40 + kb);
        g2_step(s, kb);
        wg_wait<0>();
        if (kb < 16 - NS2 && signaller) mbar_arrive_cluster(rbars + 8 * (BAR_EMPTY2 + s));
        if (++s == NS2) { s = 0; ph ^= 1; }
      }
      if (STAG < 16) {
        if (wg == LAST) nb_sync(NB_LEAD, 256);
#pragma unroll
        for (int kb = STAG; kb < 16; kb++) {
          mbar_wait(bars + 8 * (BAR_FULL2 + kb % NS2), (kb / NS2) & 1);
          g2_step(kb % NS2, 1);
        }
        if (wg != LAST) nb_arrive(NB_LEAD, 256);
      }
      wg_wait<0>();
      fence_regs(acc);
      PROF(10 + wg);
      const int lr = lane & 7, lm = lane >> 3;
      const uint32_t wbase = sb + warp * 2048;
      const uint32_t base = wbase + (lr + 8 * (lm & 1)) * 128;
#pragma unroll
      for (int j = 0; j < 16; j += 2) {
        const uint32_t a = base + (j >> 3) * 16384 + ((((j & 7) + (lm >> 1)) ^ lr) << 4);
        stsm4(a, pack_bf16(acc[4 * j], acc[4 * j + 1]), pack_bf16(acc[4 * j + 2], acc[4 * j + 3]),
              pack_bf16(acc[4 * j + 4], acc[4 * j + 5]), pack_bf16(acc[4 * j + 6], acc[4 * j + 7]));
      }
      __syncwarp();
      {
        const int rr = lane >> 4, ck = lane & 7, hf = (lane >> 3) & 1;
        uint4* og = reinterpret_cast<uint4*>(p.out + (size_t)(2 * ((rb2 & 7) * 128 + warp * 16 + rr) + (rb2 >> 3)) * (2 * DM) + DM + cb2 * 128 + hf * 64 + ck * 8);
        uint4 v[8];
#pragma unroll
        for (int i = 0; i < 8; i++) v[i] = lds128(wbase + hf * 16384 + (2 * i + rr) * 128 + ((ck ^ ((2 * i + rr) & 7)) << 4));
#pragma unroll
        for (int i = 0; i < 8; i++) og[(size_t)i * 4 * (2 * DM / 8)] = v[i];
      }
      PROF(12 + wg);
    }
    cluster_sync_all();
  }
}

typedef CUresult (*EncodeFn)(CUtensorMap*, CUtensorMapDataType, cuuint32_t, void*, const cuuint64_t*, const cuuint64_t*,
                             const cuuint32_t*, const cuuint32_t*, CUtensorMapInterleave, CUtensorMapSwizzle,
                             CUtensorMapL2promotion, CUtensorMapFloatOOBfill);

void make_map(EncodeFn enc, CUtensorMap* tm, const void* base, int rank, const cuuint64_t* dims, const cuuint64_t* strides,
              const cuuint32_t* box, CUtensorMapSwizzle swz) {
  cuuint32_t es[5] = {1, 1, 1, 1, 1};
  enc(tm, CU_TENSOR_MAP_DATA_TYPE_BFLOAT16, rank, const_cast<void*>(base), dims, strides, box, es,
      CU_TENSOR_MAP_INTERLEAVE_NONE, swz, CU_TENSOR_MAP_L2_PROMOTION_L2_256B, CU_TENSOR_MAP_FLOAT_OOB_FILL_NONE);
}

}

extern "C" void kernel_launch(void* const* d_in, const int* in_sizes, int n_in, void* d_out, int out_size) {
  static EncodeFn enc = nullptr;
  static bool coresident = true;
  if (!enc) {
    void* fn = nullptr;
    cudaDriverEntryPointQueryResult qr;
    cudaGetDriverEntryPoint("cuTensorMapEncodeTiled", &fn, cudaEnableDefault, &qr);
    enc = (EncodeFn)fn;
    cudaFuncSetAttribute(fused_kernel<0>, cudaFuncAttributeMaxDynamicSharedMemorySize, SMEM_BYTES);
    cudaFuncSetAttribute(fused_kernel<1>, cudaFuncAttributeMaxDynamicSharedMemorySize, SMEM_BYTES);
    cudaFuncSetAttribute(fused_kernel<2>, cudaFuncAttributeMaxDynamicSharedMemorySize, SMEM_BYTES);
    cudaLaunchConfig_t cfg = {};
    cfg.gridDim = dim3(NCTA);
    cfg.blockDim = dim3(NTHREADS);
    cfg.dynamicSmemBytes = SMEM_BYTES;
    cudaLaunchAttribute at;
    at.id = cudaLaunchAttributeClusterDimension;
    at.val.clusterDim.x = 2;
    at.val.clusterDim.y = 1;
    at.val.clusterDim.z = 1;
    cfg.attrs = &at;
    cfg.numAttrs = 1;
    int nclusters = 0;
    if (cudaOccupancyMaxActiveClusters(&nclusters, fused_kernel<0>, &cfg) == cudaSuccess) coresident = nclusters >= NCTA / 2;
    (void)cudaGetLastError();
  }
  CUtensorMap tmX, tmW, tmWo, tmQ, tmXh, tmWh;
  {
    cuuint64_t dims[3] = {1024, 2, 1024};
    cuuint64_t str[2] = {2048, 4096};
    cuuint32_t box[3] = {64, 1, 128};
    make_map(enc, &tmX, d_in[6], 3, dims, str, box, CU_TENSOR_MAP_SWIZZLE_128B);
  }
  {
    cuuint64_t dims[3] = {1024, 1024, 3};
    cuuint64_t str[2] = {6144, 2048};
    cuuint32_t box[3] = {64, 32, 3};
    make_map(enc, &tmW, d_in[7], 3, dims, str, box, CU_TENSOR_MAP_SWIZZLE_128B);
  }
  {
    cuuint64_t dims[3] = {64, 1024, 16};
    cuuint64_t str[2] = {2048, 128};
    cuuint32_t box[3] = {64, 64, 2};
    make_map(enc, &tmWo, d_in[8], 3, dims, str, box, CU_TENSOR_MAP_SWIZZLE_128B);
  }
  {
    cuuint64_t dims[5] = {1024, 2, 2, 8, 64};
    cuuint64_t str[4] = {2048, 16 * 2048, 2 * 2048, 32 * 2048};
    cuuint32_t box[5] = {16, 2, 2, 8, 4};
    make_map(enc, &tmQ, d_in[0], 5, dims, str, box, CU_TENSOR_MAP_SWIZZLE_NONE);
  }
  {
    cuuint64_t dims[4] = {1024, 256, 2, 4};
    cuuint64_t str[3] = {4096, 2048, 256 * 4096};
    cuuint32_t box[4] = {64, 8, 2, 4};
    make_map(enc, &tmXh, d_in[6], 4, dims, str, box, CU_TENSOR_MAP_SWIZZLE_128B);
  }
  {
    cuuint64_t dims[3] = {64, 1024, 48};
    cuuint64_t str[2] = {6144, 128};
    cuuint32_t box[3] = {64, 64, 4};
    make_map(enc, &tmWh, d_in[7], 3, dims, str, box, CU_TENSOR_MAP_SWIZZLE_128B);
  }
  Params p;
  p.q = (const __nv_bfloat16*)d_in[0];
  p.k = (const __nv_bfloat16*)d_in[1];
  p.v = (const __nv_bfloat16*)d_in[2];
  p.shift_k = (const __nv_bfloat16*)d_in[3];
  p.ssm_k = (const __nv_bfloat16*)d_in[4];
  p.ssm_D = (const __nv_bfloat16*)d_in[5];
  p.x = (const __nv_bfloat16*)d_in[6];
  p.w = (const __nv_bfloat16*)d_in[7];
  p.wo = (const __nv_bfloat16*)d_in[8];
  p.out = (__nv_bfloat16*)d_out;
  if (coresident) {
    fused_kernel<0><<<NCTA, NTHREADS, SMEM_BYTES>>>(p, tmX, tmW, tmWo, tmQ, tmXh, tmWh);
  } else {
    fused_kernel<0><<<4, NTHREADS, SMEM_BYTES>>>(p, tmX, tmW, tmWo, tmQ, tmXh, tmWh);
    fused_kernel<1><<<NCTA, NTHREADS, SMEM_BYTES>>>(p, tmX, tmW, tmWo, tmQ, tmXh, tmWh);
    fused_kernel<2><<<NCTA, NTHREADS, SMEM_BYTES>>>(p, tmX, tmW, tmWo, tmQ, tmXh, tmWh);
  }
}
```

```cpp
#include <cuda_runtime.h>
#include <cuda.h>
#include <cuda_bf16.h>
#include <stdint.h>

namespace {

constexpr int SEQ = 2048;
constexpr int DM = 1024;
constexpr int NCTA = 132;
constexpr int NTHREADS = 384;

constexpr int STG1A = 32768;
constexpr int NS1A = 3;
constexpr int STG1B = 12288;
constexpr int NS1B = 5;
constexpr int OFF_1B = NS1A * STG1A;
constexpr int STG2 = 32768;
constexpr int NS2 = 5;
constexpr int STGH = 73728;
constexpr int OFF_VP = 0;
constexpr int OFF_OP = 1 * STG2;
constexpr int OFF_Q = 3 * STG2;
constexpr int T_A4 = 0, T_TW = 16384, T_B2 = 24576, T_A1 = 28672, T_END = 32768;
constexpr int OFF_U = 163840;
constexpr int OFF_H = OFF_U + 32768;
constexpr int OFF_T = OFF_U - T_END;
constexpr int OFF_LAND = 4 * STG2;
constexpr int OFF_BAR = OFF_H + 32768;
constexpr int OFF_SC = OFF_BAR + 512;
constexpr int OFF_L0 = OFF_BAR + 1024;
constexpr int SMEM_BYTES = OFF_L0 + 2048;
static_assert(OFF_T + T_A1 == OFF_1B + NS1B * STG1B && OFF_T + T_TW == OFF_1B + 4 * STG1B && OFF_LAND == OFF_T + T_A4, "layout");
static_assert(3 * STGH <= OFF_BAR && SMEM_BYTES <= 232448, "smem");

constexpr int BAR_FULLA = 0;
constexpr int BAR_EMPTYA = 3;
constexpr int BAR_FULLB = 6;
constexpr int BAR_EMPTYB = 11;
constexpr int BAR_FULL2 = 16;
constexpr int BAR_EMPTY2 = 21;
constexpr int BAR_T = 26;
constexpr int BAR_UH = 27;
constexpr int BAR_LFREE = 28;
constexpr int BAR_LAND = 29;
constexpr int BAR_U = 30;
constexpr int BAR_Q = 31;
constexpr int BAR_STG = 32;
constexpr int BAR_DEAD = 33;
constexpr int BAR_X = 35;
constexpr int BAR_REL = 36;

constexpr int NB_G1DONE = 1;
constexpr int NB_OREADY = 2;
constexpr int NB_WG = 4;
constexpr int NB_HELP3 = 6;
constexpr int NB_FIRST = 7;
constexpr int NB_LEAD = 8;

#define PACE 390u
#define PF0 18
#define EARLYS1 0
#define PEEL 1
#define IDLEW 1
#define LA0 3
#define LA1 4
#define STAG 12
#define LAST 0
#define FINE 40
#define SCHED 1
#define REG_MATH 224
#define REG_HELP 56
constexpr int SPIN_LIMIT = 1 << 20;

__device__ __align__(1024) __nv_bfloat16 g_o[SEQ * DM];
__device__ uint32_t g_flag_o[256];
__device__ uint32_t g_flag_h[4];
__device__ uint4 g_halo[128 * 128];
__device__ __align__(128) const uint32_t g_tab[T_END / 4] = {
0x3c003c00,0x3bf13bff,0,0xafd6a648,0x3c003c00,0x3b993bce,0,0xb505b303,0x3c003c00,0x3af63b50,0,0xb7e3b67c,
0x3c003c00,0x3a0f3a8a,0,0xb93ab89b,0x3bc33bfe,0x3b773bfa,0xb3c6aa48,0xb5c2acb5,0x3a6d3b3b,0x389b3a4f,0xb8c4b6d7,0xba8ab8ec,
0x381d395f,0x26483505,0xbaddb9ed,0xbbffbb99,0x30b23564,0xb848b444,0xbbeabb88,0xbac2bbb6,0x3b0e3bf6,0x3a8a3bf1,0xb78bae46,0xb89bafd6,
0x34a53913,0xa6483732,0xbba8ba2f,0xbbffbb25,0xb78bae46,0xbac2b7e3,0xbb0ebbf6,0xb848baf6,0xbba8ba2f,0xbb50bbfa,0xb4a5b913,0x367cacb5,
0x39ed3bea,0x393a3be2,0xb95fb0b2,0xba0fb179,0xb56433c6,0xb8ec2648,0xbb88bbc3,0xba4fbbff,0xbbfeba6d,0xbb25bbce,0xaa48b8c4,0x3732b303,
0xb6d7badd,0x3444b67c,0x3b3b381d,0x3bb63b50,0x38723bd9,0x37323bce,0xbaa7b23e,0xbb25b303,0xbaa7b23e,0xbbb6b67c,0xb872bbd9,0xb444bb50,
0xb872bbd9,0xacb5ba8a,0x3aa7323e,0x3bfa389b,0x3aa7323e,0x3bf139cb,0x38723bd9,0xafd63984,0x35643bc3,0x33033bb6,0xbb88b3c6,0xbbceb444,
0xbbfeb8c4,0xbb77ba0f,0x2a48ba6d,0x35c2b93a,0x36d7b81d,0x3a8aafd6,0x3b3b3add,0x389b3bf1,0x395f3bea,0x26483b25,0xb9ed30b2,0xbbffb732,
0x2e463ba8,0xa6483b99,0xbbf6b4a5,0xbbffb505,0xba2fbb0e,0xb848bbb6,0x3913b78b,0x3ac2b444,0x3bf634a5,0x3b50393a,0x2e463ba8,0xb67c3a0f,
0xb913378b,0xbbe2afd6,0xba2fbb0e,0xb179bbf1,0xb0b23b88,0xb4443b77,0xbbeab564,0xbbb6b5c2,0xb3c6bbfe,0x2cb5bbe2,0x3bc3aa48,0x3bfa3179,
0x38c43b3b,0x2fd63bff,0xba6d36d7,0xbbf12648,0xbaddb95f,0xb505bbce,0x381db9ed,0x3b99b303,0xb61f3b64,0xb7e33b50,0xbb64b61f,0xbaf6b67c,
0x361fbb64,0x393aba8a,0x3b64361f,0x3a0f389b,0xb61f3b64,0xba4f3984,0xbb64b61f,0xb8ecb9cb,0x361fbb64,0x3b25b848,0x3b64361f,0x37323ac2,
0xb8c43b3b,0xb9843b25,0xba6db6d7,0xb9cbb732,0x3addb95f,0x3bceb7e3,0x381d39ed,0x33033af6,0xbbea3564,0xbb77acb5,0xb0b2bb88,0x35c2bbfa,
0x3bc32a48,0x389b38ec,0xb3c63bfe,0xba8a3a4f,0xba2f3b0e,0xbac23af6,0xb913b78b,0xb848b7e3,0x3bf6b4a5,0x3b50acb5,0xae463ba8,0xb67c3bfa,
0xb913b78b,0xb179ba4f,0x3a2fbb0e,0x3be2b8ec,0xae463ba8,0xb9cb3b99,0xbbf634a5,0xb984b505,0xbb3b3add,0xbb993ac2,0xb6d7b81d,0xb505b848,
0x39ed30b2,0x37e335c2,0xb95f3bea,0xbaf63b77,0x3564bbc3,0x3a0fbbe2,0x3b88b3c6,0x393a3179,0xbbfe38c4,0xba4f2648,0xaa48ba6d,0x38ecbbff,
0xbbd93aa7,0xbbfa3a8a,0xb23eb872,0xacb5b89b,0x323e3872,0xafd639cb,0xbbd93aa7,0xbbf13984,0x3bd9baa7,0x3b99b848,0x323e3872,0xb5053ac2,
0xb23eb872,0x37e3bb77,0x3bd9baa7,0x3af6b5c2,0xbbfe3a6d,0xbbe23a4f,0x2a48b8c4,0x3179b8ec,0xb6d73add,0xb9843b99,0xbb3b381d,0xb9cb3505,
0x395fb0b2,0x33033444,0xb9ed3bea,0xbbce3bb6,0x3b88bbc3,0x3b77b93a,0x356433c6,0xb5c23a0f,0xbba83a2f,0xbb503a0f,0x34a5b913,0x367cb93a,
0xbb0e3bf6,0xbbe23bf1,0xb78b2e46,0xb179afd6,0xb4a53913,0xb9cb3b25,0xbba83a2f,0xb9843732,0x378bae46,0xb30337e3,0xbb0e3bf6,0xbbce3af6,
0xbadd39ed,0xba4f39cb,0x381db95f,0x38ecb984,0xbbea3b88,0xbb253ac2,0x30b2b564,0x3732b848,0xbbc33bfe,0xbbb63b77,0xb3c62a48,0x3444b5c2,
0xba6d3b3b,0xbbfa3be2,0xb8c436d7,0x2cb5b179,0xb9a839a8,0xb8ec3984,0x39a8b9a8,0x3a4fb9cb,0xb9a839a8,0xb7323848,0x39a8b9a8,0x3b25bac2,
0xb9a839a8,0xb44435c2,0x39a8b9a8,0x3bb6bb77,0xb9a839a8,0xacb53179,0x39a8b9a8,0x3bfabbe2,0xb81d395f,0xb67c393a,0x3addb9ed,0x3b50ba0f,
0xb0b23564,0x31792fd6,0x3beabb88,0x3be2bbf1,0x33c6aa48,0x3984b732,0x3bc3bbfe,0x39cbbb25,0x38c4b6d7,0x3bcebaf6,0x3a6dbb3b,0x3303b7e3,
0xb4a53913,0xb17938ec,0x3ba8ba2f,0x3be2ba4f,0x378bae46,0x39cbb505,0x3b0ebbf6,0x3984bb99,0x3ba8ba2f,0x3bcebbb6,0x34a5b913,0xb303b444,
0x3b0ebbf6,0x35c2ba0f,0xb78b2e46,0xbb77393a,0xaa4838c4,0x2cb5389b,0x3bfeba6d,0x3bfaba8a,0x3b3bb81d,0x3bf1b984,0x36d7badd,0x2fd6b9cb,
0x39edbbea,0x3505bac2,0xb95f30b2,0xbb993848,0xb564b3c6,0xbaf635c2,0xbb883bc3,0xb7e33b77,0x323e3872,0x35053848,0x3bd9baa7,0x3b99bac2,
0x3bd9baa7,0x3af6bb77,0xb23eb872,0xb7e3b5c2,0xb23eb872,0xb93ab179,0xbbd93aa7,0xba0f3be2,0xbbd93aa7,0xb8ec3bff,0x323e3872,0x3a4fa648,
0x36d7381d,0x384837e3,0x3b3bbadd,0x3ac2baf6,0x395fbbea,0x367cbbfa,0xb9edb0b2,0xbb502cb5,0xbb8833c6,0xbbe238ec,0xb5643bc3,0x31793a4f,
0x2a483a6d,0x39843505,0x3bfeb8c4,0x39cbbb99,0x3913378b,0x39cb3732,0x3a2fbb0e,0x3984bb25,0x2e46bba8,0xb303baf6,0xbbf634a5,0xbbce37e3,
0xba2f3b0e,0xb5c23bfa,0x3913378b,0x3b772cb5,0x3bf6b4a5,0x3a8aba4f,0x2e46bba8,0xb89bb8ec,0x3a6d36d7,0x3af6367c,0x38c4bb3b,0x37e3bb50,
0xb81db9ed,0xba0fb89b,0xbadd395f,0xb93a3a8a,0x30b23b88,0x38ec39cb,0x3beab564,0x3a4fb984,0x33c6bbfe,0xb732bac2,0xbbc3aa48,0xbb253848,
0x3b64361f,0x3bb635c2,0x361fbb64,0x3444bb77,0xbb64b61f,0xbbfab179,0xb61f3b64,0xacb53be2,0x3b64361f,0x3bf1a648,0x361fbb64,0xafd6bbff,
0xbb64b61f,0xbb993303,0xb61f3b64,0x35053bce,0x3bea3564,0x3bff3505,0x30b2bb88,0x2648bb99,0xbbc32a48,0xbac23444,0x33c63bfe,0x38483bb6,
0x3a6db6d7,0x367cba0f,0xb8c4bb3b,0xbb50b93a,0xb81d39ed,0x31793bf1,0x3add395f,0x3be22fd6,0x3bf634a5,0x3bce3444,0xae46bba8,0xb303bbb6,
0xb913378b,0xb5c2393a,0x3a2f3b0e,0x3b773a0f,0xae46bba8,0xb89bbbf1,0xbbf6b4a5,0xba8a2fd6,0x3a2f3b0e,0x3bff3732,0x3913b78b,0xa648bb25,
0x3b8833c6,0x3b253303,0xb564bbc3,0xb732bbce,0xaa483a6d,0x34443b50,0x3bfe38c4,0x3bb6367c,0xbb3bbadd,0xbbfab89b,0xb6d7381d,0x2cb53a8a,
0x39edb0b2,0x2fd6b984,0xb95fbbea,0xbbf1b9cb,0x3aa7323e,0x3a0f3179,0xb872bbd9,0xb93abbe2,0x38723bd9,0x3a4f3bff,0x3aa7323e,0x38eca648,
0xbaa7b23e,0xb7323303,0x38723bd9,0x3b253bce,0xb872bbd9,0xbbb6bb50,0xbaa7b23e,0xb444367c,0x395f30b2,0x389b2fd6,0xb9edbbea,0xba8abbf1,
0x3b883bc3,0x3bff3b25,0x3564b3c6,0x2648b732,0x2a4838c4,0x38483af6,0x3bfe3a6d,0x3ac237e3,0xbb3bb81d,0xb67c2cb5,0x36d73add,0x3b503bfa,
0x378b2e46,0x35c22cb5,0xbb0ebbf6,0xbb77bbfa,0x3ba83a2f,0x3a8a38ec,0xb4a5b913,0xb89bba4f,0x3b0e3bf6,0x3bff3b99,0x378b2e46,0xa648b505,
0x34a53913,0x3ac23bb6,0x3ba83a2f,0x38483444,0x33c62a48,0x2fd62648,0xbbc3bbfe,0xbbf1bbff,0x38c436d7,0x35053303,0xba6dbb3b,0xbb99bbce,
0x3add39ed,0x37e3367c,0xb81db95f,0xbaf6bb50,0x3bea3b88,0x393a389b,0xb0b2b564,0xba0fba8a,0x3c003c00,0xbbf1bbff,0,0x2fd62648,
0x3c003c00,0xbb99bbce,0,0x35053303,0x3c003c00,0xbaf6bb50,0,0x37e3367c,0x3c003c00,0xba0fba8a,0,0x393a389b,
0x3bc33bfe,0xbb77bbfa,0xb3c6aa48,0x35c22cb5,0x3a6d3b3b,0xb89bba4f,0xb8c4b6d7,0x3a8a38ec,0x381d395f,0xa648b505,0xbaddb9ed,0x3bff3b99,
0x30b23564,0x38483444,0xbbeabb88,0x3ac23bb6,0x3b0e3bf6,0xba8abbf1,0xb78bae46,0x389b2fd6,0x34a53913,0x2648b732,0xbba8ba2f,0x3bff3b25,
0xb78bae46,0x3ac237e3,0xbb0ebbf6,0x38483af6,0xbba8ba2f,0x3b503bfa,0xb4a5b913,0xb67c2cb5,0x39ed3bea,0xb93abbe2,0xb95fb0b2,0x3a0f3179,
0xb56433c6,0x38eca648,0xbb88bbc3,0x3a4f3bff,0xbbfeba6d,0x3b253bce,0xaa48b8c4,0xb7323303,0xb6d7badd,0xb444367c,0x3b3b381d,0xbbb6bb50,
0x38723bd9,0xb732bbce,0xbaa7b23e,0x3b253303,0xbaa7b23e,0x3bb6367c,0xb872bbd9,0x34443b50,0xb872bbd9,0x2cb53a8a,0x3aa7323e,0xbbfab89b,
0x3aa7323e,0xbbf1b9cb,0x38723bd9,0x2fd6b984,0x35643bc3,0xb303bbb6,0xbb88b3c6,0x3bce3444,0xbbfeb8c4,0x3b773a0f,0x2a48ba6d,0xb5c2393a,
0x36d7b81d,0xba8a2fd6,0x3b3b3add,0xb89bbbf1,0x395f3bea,0xa648bb25,0xb9ed30b2,0x3bff3732,0x2e463ba8,0x2648bb99,0xbbf6b4a5,0x3bff3505,
0xba2fbb0e,0x38483bb6,0x3913b78b,0xbac23444,0x3bf634a5,0xbb50b93a,0x2e463ba8,0x367cba0f,0xb913378b,0x3be22fd6,0xba2fbb0e,0x31793bf1,
0xb0b23b88,0x3444bb77,0xbbeab564,0x3bb635c2,0xb3c6bbfe,0xacb53be2,0x3bc3aa48,0xbbfab179,0x38c43b3b,0xafd6bbff,0xba6d36d7,0x3bf1a648,
0xbaddb95f,0x35053bce,0x381db9ed,0xbb993303,0xb61f3b64,0x37e3bb50,0xbb64b61f,0x3af6367c,0x361fbb64,0xb93a3a8a,0x3b64361f,0xba0fb89b,
0xb61f3b64,0x3a4fb984,0xbb64b61f,0x38ec39cb,0x361fbb64,0xbb253848,0x3b64361f,0xb732bac2,0xb8c43b3b,0x3984bb25,0xba6db6d7,0x39cb3732,
0x3addb95f,0xbbce37e3,0x381d39ed,0xb303baf6,0xbbea3564,0x3b772cb5,0xb0b2bb88,0xb5c23bfa,0x3bc32a48,0xb89bb8ec,0xb3c63bfe,0x3a8aba4f,
0xba2f3b0e,0x3ac2baf6,0xb913b78b,0x384837e3,0x3bf6b4a5,0xbb502cb5,0xae463ba8,0x367cbbfa,0xb913b78b,0x31793a4f,0x3a2fbb0e,0xbbe238ec,
0xae463ba8,0x39cbbb99,0xbbf634a5,0x39843505,0xbb3b3add,0x3b99bac2,0xb6d7b81d,0x35053848,0x39ed30b2,0xb7e3b5c2,0xb95f3bea,0x3af6bb77,
0x3564bbc3,0xba0f3be2,0x3b88b3c6,0xb93ab179,0xbbfe38c4,0x3a4fa648,0xaa48ba6d,0xb8ec3bff,0xbbd93aa7,0x3bfaba8a,0xb23eb872,0x2cb5389b,
0x323e3872,0x2fd6b9cb,0xbbd93aa7,0x3bf1b984,0x3bd9baa7,0xbb993848,0x323e3872,0x3505bac2,0xb23eb872,0xb7e33b77,0x3bd9baa7,0xbaf635c2,
0xbbfe3a6d,0x3be2ba4f,0x2a48b8c4,0xb17938ec,0xb6d73add,0x3984bb99,0xbb3b381d,0x39cbb505,0x395fb0b2,0xb303b444,0xb9ed3bea,0x3bcebbb6,
0x3b88bbc3,0xbb77393a,0x356433c6,0x35c2ba0f,0xbba83a2f,0x3b50ba0f,0x34a5b913,0xb67c393a,0xbb0e3bf6,0x3be2bbf1,0xb78b2e46,0x31792fd6,
0xb4a53913,0x39cbbb25,0xbba83a2f,0x3984b732,0x378bae46,0x3303b7e3,0xbb0e3bf6,0x3bcebaf6,0xbadd39ed,0x3a4fb9cb,0x381db95f,0xb8ec3984,
0xbbea3b88,0x3b25bac2,0x30b2b564,0xb7323848,0xbbc33bfe,0x3bb6bb77,0xb3c62a48,0xb44435c2,0xba6d3b3b,0x3bfabbe2,0xb8c436d7,0xacb53179,
0xb9a839a8,0x38ecb984,0x39a8b9a8,0xba4f39cb,0xb9a839a8,0x3732b848,0x39a8b9a8,0xbb253ac2,0xb9a839a8,0x3444b5c2,0x39a8b9a8,0xbbb63b77,
0xb9a839a8,0x2cb5b179,0x39a8b9a8,0xbbfa3be2,0xb81d395f,0x367cb93a,0x3addb9ed,0xbb503a0f,0xb0b23564,0xb179afd6,0x3beabb88,0xbbe23bf1,
0x33c6aa48,0xb9843732,0x3bc3bbfe,0xb9cb3b25,0x38c4b6d7,0xbbce3af6,0x3a6dbb3b,0xb30337e3,0xb4a53913,0x3179b8ec,0x3ba8ba2f,0xbbe23a4f,
0x378bae46,0xb9cb3505,0x3b0ebbf6,0xb9843b99,0x3ba8ba2f,0xbbce3bb6,0x34a5b913,0x33033444,0x3b0ebbf6,0xb5c23a0f,0xb78b2e46,0x3b77b93a,
0xaa4838c4,0xacb5b89b,0x3bfeba6d,0xbbfa3a8a,0x3b3bb81d,0xbbf13984,0x36d7badd,0xafd639cb,0x39edbbea,0xb5053ac2,0xb95f30b2,0x3b99b848,
0xb564b3c6,0x3af6b5c2,0xbb883bc3,0x37e3bb77,0x323e3872,0xb505b848,0x3bd9baa7,0xbb993ac2,0x3bd9baa7,0xbaf63b77,0xb23eb872,0x37e335c2,
0xb23eb872,0x393a3179,0xbbd93aa7,0x3a0fbbe2,0xbbd93aa7,0x38ecbbff,0x323e3872,0xba4f2648,0x36d7381d,0xb848b7e3,0x3b3bbadd,0xbac23af6,
0x395fbbea,0xb67c3bfa,0xb9edb0b2,0x3b50acb5,0xbb8833c6,0x3be2b8ec,0xb5643bc3,0xb179ba4f,0x2a483a6d,0xb984b505,0x3bfeb8c4,0xb9cb3b99,
0x3913378b,0xb9cbb732,0x3a2fbb0e,0xb9843b25,0x2e46bba8,0x33033af6,0xbbf634a5,0x3bceb7e3,0xba2f3b0e,0x35c2bbfa,0x3913378b,0xbb77acb5,
0x3bf6b4a5,0xba8a3a4f,0x2e46bba8,0x389b38ec,0x3a6d36d7,0xbaf6b67c,0x38c4bb3b,0xb7e33b50,0xb81db9ed,0x3a0f389b,0xbadd395f,0x393aba8a,
0x30b23b88,0xb8ecb9cb,0x3beab564,0xba4f3984,0x33c6bbfe,0x37323ac2,0xbbc3aa48,0x3b25b848,0x3b64361f,0xbbb6b5c2,0x361fbb64,0xb4443b77,
0xbb64b61f,0x3bfa3179,0xb61f3b64,0x2cb5bbe2,0x3b64361f,0xbbf12648,0x361fbb64,0x2fd63bff,0xbb64b61f,0x3b99b303,0xb61f3b64,0xb505bbce,
0x3bea3564,0xbbffb505,0x30b2bb88,0xa6483b99,0xbbc32a48,0x3ac2b444,0x33c63bfe,0xb848bbb6,0x3a6db6d7,0xb67c3a0f,0xb8c4bb3b,0x3b50393a,
0xb81d39ed,0xb179bbf1,0x3add395f,0xbbe2afd6,0x3bf634a5,0xbbceb444,0xae46bba8,0x33033bb6,0xb913378b,0x35c2b93a,0x3a2f3b0e,0xbb77ba0f,
0xae46bba8,0x389b3bf1,0xbbf6b4a5,0x3a8aafd6,0x3a2f3b0e,0xbbffb732,0x3913b78b,0x26483b25,0x3b8833c6,0xbb25b303,0xb564bbc3,0x37323bce,
0xaa483a6d,0xb444bb50,0x3bfe38c4,0xbbb6b67c,0xbb3bbadd,0x3bfa389b,0xb6d7381d,0xacb5ba8a,0x39edb0b2,0xafd63984,0xb95fbbea,0x3bf139cb,
0x3aa7323e,0xba0fb179,0xb872bbd9,0x393a3be2,0x38723bd9,0xba4fbbff,0x3aa7323e,0xb8ec2648,0xbaa7b23e,0x3732b303,0x38723bd9,0xbb25bbce,
0xb872bbd9,0x3bb63b50,0xbaa7b23e,0x3444b67c,0x395f30b2,0xb89bafd6,0xb9edbbea,0x3a8a3bf1,0x3b883bc3,0xbbffbb25,0x3564b3c6,0xa6483732,
0x2a4838c4,0xb848baf6,0x3bfe3a6d,0xbac2b7e3,0xbb3bb81d,0x367cacb5,0x36d73add,0xbb50bbfa,0x378b2e46,0xb5c2acb5,0xbb0ebbf6,0x3b773bfa,
0x3ba83a2f,0xba8ab8ec,0xb4a5b913,0x389b3a4f,0x3b0e3bf6,0xbbffbb99,0x378b2e46,0x26483505,0x34a53913,0xbac2bbb6,0x3ba83a2f,0xb848b444,
0x33c62a48,0xafd6a648,0xbbc3bbfe,0x3bf13bff,0x38c436d7,0xb505b303,0xba6dbb3b,0x3b993bce,0x3add39ed,0xb7e3b67c,0xb81db95f,0x3af63b50,
0x3bea3b88,0xb93ab89b,0xb0b2b564,0x3a0f3a8a,0x3c003c00,0x38ec3984,0,0xba4fb9cb,0x3c003c00,0x37323848,0,0xbb25bac2,
0x3c003c00,0x344435c2,0,0xbbb6bb77,0x3c003c00,0x2cb53179,0,0xbbfabbe2,0xb3c6aa48,0xbb50ba0f,0xbbc3bbfe,0xb67cb93a,
0xb8c4b6d7,0xbbe2bbf1,0xba6dbb3b,0x3179afd6,0xbaddb9ed,0xb9cbbb25,0xb81db95f,0x39843732,0xbbeabb88,0xb303b7e3,0xb0b2b564,0x3bce3af6,
0xbb0ebbf6,0xb179b8ec,0x378b2e46,0x3be23a4f,0xb4a5b913,0x39cb3505,0x3ba83a2f,0x39843b99,0x378b2e46,0x3bce3bb6,0x3b0e3bf6,0xb3033444,
0x3ba83a2f,0x35c23a0f,0x34a53913,0xbb77b93a,0x395f30b2,0x3bfa3a8a,0x39ed3bea,0xacb5389b,0x3b883bc3,0x2fd639cb,0xb56433c6,0xbbf1b984,
0x2a4838c4,0xbb99b848,0xbbfeba6d,0xb505bac2,0xbb3bb81d,0xb7e3bb77,0xb6d7badd,0x3af635c2,0x38723bd9,0xb5053848,0xbaa7b23e,0xbb99bac2,
0xbaa7b23e,0xbaf6bb77,0xb872bbd9,0x37e3b5c2,0xb872bbd9,0x393ab179,0x3aa7323e,0x3a0f3be2,0x3aa7323e,0x38ec3bff,0x38723bd9,0xba4fa648,
0xbb88b3c6,0xbac2baf6,0xb564bbc3,0x3848b7e3,0x2a48ba6d,0x3b502cb5,0x3bfe38c4,0x367c3bfa,0x3b3b3add,0xb1793a4f,0xb6d7381d,0xbbe2b8ec,
0xb9ed30b2,0xb9cbbb99,0xb95fbbea,0x3984b505,0xae46bba8,0x39cbb732,0x3bf634a5,0x39843b25,0x3a2f3b0e,0xb3033af6,0xb913378b,0xbbceb7e3,
0xbbf6b4a5,0xb5c2bbfa,0xae46bba8,0x3b77acb5,0x3913b78b,0x3a8a3a4f,0x3a2f3b0e,0xb89b38ec,0x3bea3564,0x37e33b50,0xb0b23b88,0xbaf6367c,
0xbbc32a48,0xb93aba8a,0xb3c6bbfe,0x3a0fb89b,0x3a6db6d7,0x3a4f3984,0x38c43b3b,0xb8ec39cb,0xb81d39ed,0xbb25b848,0xbaddb95f,0x3732bac2,
0xb61f3b64,0xbbb635c2,0xbb64b61f,0xb444bb77,0x361fbb64,0x3bfab179,0x3b64361f,0x2cb53be2,0xb61f3b64,0xbbf1a648,0xbb64b61f,0x2fd6bbff,
0x361fbb64,0x3b993303,0x3b64361f,0xb5053bce,0xba6db6d7,0xa648bb99,0x38c4bb3b,0x3bffb505,0x381d39ed,0xb8483bb6,0xbadd395f,0xbac2b444,
0xb0b2bb88,0x3b50b93a,0x3beab564,0x367c3a0f,0xb3c63bfe,0xbbe22fd6,0xbbc3aa48,0x3179bbf1,0x3a2fbb0e,0x3bceb444,0x3913378b,0xb3033bb6,
0xbbf634a5,0xb5c2b93a,0x2e46bba8,0x3b77ba0f,0x3913378b,0xb89b3bf1,0xba2f3b0e,0xba8aafd6,0x2e46bba8,0x3bffb732,0x3bf6b4a5,0xa6483b25,
0x36d7381d,0xb7323bce,0xbb3b3add,0xbb253303,0x395fbbea,0x3bb6b67c,0x39ed30b2,0xb4443b50,0xbb8833c6,0x2cb5ba8a,0x3564bbc3,0x3bfab89b,
0x2a483a6d,0xbbf139cb,0xbbfe38c4,0xafd6b984,0xbbd93aa7,0xba0f3179,0xb23eb872,0x393abbe2,0x323e3872,0xba4f3bff,0xbbd93aa7,0xb8eca648,
0x3bd9baa7,0x37323303,0x323e3872,0xbb253bce,0xb23eb872,0x3bb6bb50,0x3bd9baa7,0x3444367c,0x2a48b8c4,0x3a8abbf1,0x3bfeba6d,0x389bafd6,
0xbb3b381d,0xa648b732,0x36d7badd,0x3bffbb25,0xb9ed3bea,0xbac237e3,0xb95f30b2,0x3848baf6,0x356433c6,0xbb503bfa,0xbb883bc3,0xb67cacb5,
0x3ba8ba2f,0x35c2acb5,0xb4a53913,0xbb773bfa,0x3b0ebbf6,0x3a8ab8ec,0x378bae46,0xb89b3a4f,0x34a5b913,0x3bffbb99,0x3ba8ba2f,0xa6483505,
0xb78b2e46,0x3ac2bbb6,0x3b0ebbf6,0x3848b444,0xb81d395f,0xbbf13bff,0xbadd39ed,0xafd62648,0xb0b23564,0xbb993bce,0xbbea3b88,0xb5053303,
0x33c6aa48,0xbaf63b50,0xbbc33bfe,0xb7e3367c,0x38c4b6d7,0xba0f3a8a,0xba6d3b3b,0xb93a389b,0xb9a839a8,0x2fd6a648,0x39a8b9a8,0x3bf1bbff,
0xb9a839a8,0x3505b303,0x39a8b9a8,0x3b99bbce,0xb9a839a8,0x37e3b67c,0x39a8b9a8,0x3af6bb50,0xb9a839a8,0x393ab89b,0x39a8b9a8,0x3a0fba8a,
0x3addb9ed,0x3b77bbfa,0x381db95f,0xb5c22cb5,0x3beabb88,0x389bba4f,0x30b2b564,0xba8a38ec,0x3bc3bbfe,0x2648b505,0xb3c62a48,0xbbff3b99,
0x3a6dbb3b,0xb8483444,0xb8c436d7,0xbac23bb6,0x34a5b913,0xb89b2fd6,0xbba83a2f,0xba8a3bf1,0xb78b2e46,0xbbff3b25,0xbb0e3bf6,0x26483732,
0xbba83a2f,0xb8483af6,0xb4a53913,0x3ac2b7e3,0xbb0e3bf6,0x367c2cb5,0x378bae46,0x3b50bbfa,0xbbfe3a6d,0xb93a3be2,0xaa4838c4,0x3a0fb179,
0xb6d73add,0x38ec2648,0x3b3bb81d,0x3a4fbbff,0x395fb0b2,0x3b25bbce,0x39edbbea,0xb732b303,0x3b88bbc3,0xb444b67c,0xb564b3c6,0xbbb63b50,
0x323e3872,0x3b25b303,0x3bd9baa7,0x3732bbce,0x3bd9baa7,0x3444bb50,0xb23eb872,0xbbb6367c,0xb23eb872,0xbbfa389b,0xbbd93aa7,0xacb53a8a,
0xbbd93aa7,0x2fd63984,0x323e3872,0x3bf1b9cb,0x3b3bbadd,0x3303bbb6,0xb6d7b81d,0xbbce3444,0xb9edb0b2,0xbb773a0f,0xb95f3bea,0x35c2393a,
0xb5643bc3,0x3a8a2fd6,0x3b88b3c6,0x389bbbf1,0x3bfeb8c4,0x2648bb25,0xaa48ba6d,0xbbff3732,0xb913b78b,0xbbff3505,0xba2f3b0e,0x26483b99,
0xae463ba8,0x3ac23444,0x3bf6b4a5,0x3848bbb6,0x3a2fbb0e,0xb67cba0f,0xb913b78b,0xbb50393a,0xbbf634a5,0xb1793bf1,0xae463ba8,0x3be2afd6,
0xb8c43b3b,0x34443b77,0x3a6d36d7,0x3bb6b5c2,0x3addb95f,0xacb5bbe2,0xb81db9ed,0xbbfa3179,0xbbea3564,0xafd63bff,0x30b23b88,0x3bf12648,
0x3bc32a48,0x3505bbce,0x33c6bbfe,0xbb99b303,0x3b64361f,0x3af6b67c,0x361fbb64,0xb7e3bb50,0xbb64b61f,0xba0f389b,0xb61f3b64,0x393a3a8a,
0x3b64361f,0x38ecb9cb,0x361fbb64,0xba4fb984,0xbb64b61f,0xb7323ac2,0xb61f3b64,0x3b253848,0x30b2bb88,0xb984bb25,0xbbeab564,0xb9cb3732,
0x33c63bfe,0x3bce37e3,0x3bc3aa48,0x3303baf6,0xb8c4bb3b,0xbb772cb5,0xba6d36d7,0x35c23bfa,0x3add395f,0x389bb8ec,0x381db9ed,0xba8aba4f,
0xbbf6b4a5,0xb84837e3,0x2e463ba8,0x3ac23af6,0x3913b78b,0xb67cbbfa,0xba2fbb0e,0xbb50acb5,0x2e463ba8,0x3be238ec,0x3bf634a5,0x3179ba4f,
0xba2fbb0e,0xb9843505,0xb913378b,0x39cb3b99,0x35643bc3,0x3b993ac2,0x3b8833c6,0x3505b848,0xbbfeb8c4,0xb7e335c2,0xaa483a6d,0x3af63b77,
0x36d7b81d,0xba0fbbe2,0xbb3bbadd,0xb93a3179,0x395f3bea,0x3a4f2648,0x39edb0b2,0xb8ecbbff,0x3aa7323e,0x2cb5b89b,0xb872bbd9,0xbbfaba8a,
0x38723bd9,0x3bf13984,0x3aa7323e,0xafd6b9cb,0xbaa7b23e,0x35053ac2,0x38723bd9,0x3b993848,0xb872bbd9,0xbaf6b5c2,0xbaa7b23e,0x37e33b77,
0xb9edbbea,0xbbe2ba4f,0xb95fb0b2,0x317938ec,0x3564b3c6,0xb984bb99,0xbb88bbc3,0xb9cbb505,0x3bfe3a6d,0x3303b444,0xaa48b8c4,0xbbcebbb6,
0x36d73add,0x3b77393a,0x3b3b381d,0xb5c2ba0f,0xb78bae46,0x367c393a,0x3b0e3bf6,0x3b503a0f,0xbba8ba2f,0xb1792fd6,0x34a53913,0x3be23bf1,
0xbb0ebbf6,0xb984b732,0xb78bae46,0x39cb3b25,0xb4a5b913,0xbbcebaf6,0xbba8ba2f,0x330337e3,0x3bc33bfe,0x3a4f39cb,0x33c62a48,0xb8ecb984,
0x3a6d3b3b,0x3b253ac2,0x38c436d7,0xb732b848,0x381d395f,0x3bb63b77,0x3add39ed,0xb444b5c2,0x30b23564,0x3bfa3be2,0x3bea3b88,0xacb5b179,
0x3c003c00,0xb8ecb984,0,0x3a4f39cb,0x3c003c00,0xb732b848,0,0x3b253ac2,0x3c003c00,0xb444b5c2,0,0x3bb63b77,
0x3c003c00,0xacb5b179,0,0x3bfa3be2,0xb3c6aa48,0x3b503a0f,0xbbc3bbfe,0x367c393a,0xb8c4b6d7,0x3be23bf1,0xba6dbb3b,0xb1792fd6,
0xbaddb9ed,0x39cb3b25,0xb81db95f,0xb984b732,0xbbeabb88,0x330337e3,0xb0b2b564,0xbbcebaf6,0xbb0ebbf6,0x317938ec,0x378b2e46,0xbbe2ba4f,
0xb4a5b913,0xb9cbb505,0x3ba83a2f,0xb984bb99,0x378b2e46,0xbbcebbb6,0x3b0e3bf6,0x3303b444,0x3ba83a2f,0xb5c2ba0f,0x34a53913,0x3b77393a,
0x395f30b2,0xbbfaba8a,0x39ed3bea,0x2cb5b89b,0x3b883bc3,0xafd6b9cb,0xb56433c6,0x3bf13984,0x2a4838c4,0x3b993848,0xbbfeba6d,0x35053ac2,
0xbb3bb81d,0x37e33b77,0xb6d7badd,0xbaf6b5c2,0x38723bd9,0x3505b848,0xbaa7b23e,0x3b993ac2,0xbaa7b23e,0x3af63b77,0xb872bbd9,0xb7e335c2,
0xb872bbd9,0xb93a3179,0x3aa7323e,0xba0fbbe2,0x3aa7323e,0xb8ecbbff,0x38723bd9,0x3a4f2648,0xbb88b3c6,0x3ac23af6,0xb564bbc3,0xb84837e3,
0x2a48ba6d,0xbb50acb5,0x3bfe38c4,0xb67cbbfa,0x3b3b3add,0x3179ba4f,0xb6d7381d,0x3be238ec,0xb9ed30b2,0x39cb3b99,0xb95fbbea,0xb9843505,
0xae46bba8,0xb9cb3732,0x3bf634a5,0xb984bb25,0x3a2f3b0e,0x3303baf6,0xb913378b,0x3bce37e3,0xbbf6b4a5,0x35c23bfa,0xae46bba8,0xbb772cb5,
0x3913b78b,0xba8aba4f,0x3a2f3b0e,0x389bb8ec,0x3bea3564,0xb7e3bb50,0xb0b23b88,0x3af6b67c,0xbbc32a48,0x393a3a8a,0xb3c6bbfe,0xba0f389b,
0x3a6db6d7,0xba4fb984,0x38c43b3b,0x38ecb9cb,0xb81d39ed,0x3b253848,0xbaddb95f,0xb7323ac2,0xb61f3b64,0x3bb6b5c2,0xbb64b61f,0x34443b77,
0x361fbb64,0xbbfa3179,0x3b64361f,0xacb5bbe2,0xb61f3b64,0x3bf12648,0xbb64b61f,0xafd63bff,0x361fbb64,0xbb99b303,0x3b64361f,0x3505bbce,
0xba6db6d7,0x26483b99,0x38c4bb3b,0xbbff3505,0x381d39ed,0x3848bbb6,0xbadd395f,0x3ac23444,0xb0b2bb88,0xbb50393a,0x3beab564,0xb67cba0f,
0xb3c63bfe,0x3be2afd6,0xbbc3aa48,0xb1793bf1,0x3a2fbb0e,0xbbce3444,0x3913378b,0x3303bbb6,0xbbf634a5,0x35c2393a,0x2e46bba8,0xbb773a0f,
0x3913378b,0x389bbbf1,0xba2f3b0e,0x3a8a2fd6,0x2e46bba8,0xbbff3732,0x3bf6b4a5,0x2648bb25,0x36d7381d,0x3732bbce,0xbb3b3add,0x3b25b303,
0x395fbbea,0xbbb6367c,0x39ed30b2,0x3444bb50,0xbb8833c6,0xacb53a8a,0x3564bbc3,0xbbfa389b,0x2a483a6d,0x3bf1b9cb,0xbbfe38c4,0x2fd63984,
0xbbd93aa7,0x3a0fb179,0xb23eb872,0xb93a3be2,0x323e3872,0x3a4fbbff,0xbbd93aa7,0x38ec2648,0x3bd9baa7,0xb732b303,0x323e3872,0x3b25bbce,
0xb23eb872,0xbbb63b50,0x3bd9baa7,0xb444b67c,0x2a48b8c4,0xba8a3bf1,0x3bfeba6d,0xb89b2fd6,0xbb3b381d,0x26483732,0x36d7badd,0xbbff3b25,
0xb9ed3bea,0x3ac2b7e3,0xb95f30b2,0xb8483af6,0x356433c6,0x3b50bbfa,0xbb883bc3,0x367c2cb5,0x3ba8ba2f,0xb5c22cb5,0xb4a53913,0x3b77bbfa,
0x3b0ebbf6,0xba8a38ec,0x378bae46,0x389bba4f,0x34a5b913,0xbbff3b99,0x3ba8ba2f,0x2648b505,0xb78b2e46,0xbac23bb6,0x3b0ebbf6,0xb8483444,
0xb81d395f,0x3bf1bbff,0xbadd39ed,0x2fd6a648,0xb0b23564,0x3b99bbce,0xbbea3b88,0x3505b303,0x33c6aa48,0x3af6bb50,0xbbc33bfe,0x37e3b67c,
0x38c4b6d7,0x3a0fba8a,0xba6d3b3b,0x393ab89b,0xb9a839a8,0xafd62648,0x39a8b9a8,0xbbf13bff,0xb9a839a8,0xb5053303,0x39a8b9a8,0xbb993bce,
0xb9a839a8,0xb7e3367c,0x39a8b9a8,0xbaf63b50,0xb9a839a8,0xb93a389b,0x39a8b9a8,0xba0f3a8a,0x3addb9ed,0xbb773bfa,0x381db95f,0x35c2acb5,
0x3beabb88,0xb89b3a4f,0x30b2b564,0x3a8ab8ec,0x3bc3bbfe,0xa6483505,0xb3c62a48,0x3bffbb99,0x3a6dbb3b,0x3848b444,0xb8c436d7,0x3ac2bbb6,
0x34a5b913,0x389bafd6,0xbba83a2f,0x3a8abbf1,0xb78b2e46,0x3bffbb25,0xbb0e3bf6,0xa648b732,0xbba83a2f,0x3848baf6,0xb4a53913,0xbac237e3,
0xbb0e3bf6,0xb67cacb5,0x378bae46,0xbb503bfa,0xbbfe3a6d,0x393abbe2,0xaa4838c4,0xba0f3179,0xb6d73add,0xb8eca648,0x3b3bb81d,0xba4f3bff,
0x395fb0b2,0xbb253bce,0x39edbbea,0x37323303,0x3b88bbc3,0x3444367c,0xb564b3c6,0x3bb6bb50,0x323e3872,0xbb253303,0x3bd9baa7,0xb7323bce,
0x3bd9baa7,0xb4443b50,0xb23eb872,0x3bb6b67c,0xb23eb872,0x3bfab89b,0xbbd93aa7,0x2cb5ba8a,0xbbd93aa7,0xafd6b984,0x323e3872,0xbbf139cb,
0x3b3bbadd,0xb3033bb6,0xb6d7b81d,0x3bceb444,0xb9edb0b2,0x3b77ba0f,0xb95f3bea,0xb5c2b93a,0xb5643bc3,0xba8aafd6,0x3b88b3c6,0xb89b3bf1,
0x3bfeb8c4,0xa6483b25,0xaa48ba6d,0x3bffb732,0xb913b78b,0x3bffb505,0xba2f3b0e,0xa648bb99,0xae463ba8,0xbac2b444,0x3bf6b4a5,0xb8483bb6,
0x3a2fbb0e,0x367c3a0f,0xb913b78b,0x3b50b93a,0xbbf634a5,0x3179bbf1,0xae463ba8,0xbbe22fd6,0xb8c43b3b,0xb444bb77,0x3a6d36d7,0xbbb635c2,
0x3addb95f,0x2cb53be2,0xb81db9ed,0x3bfab179,0xbbea3564,0x2fd6bbff,0x30b23b88,0xbbf1a648,0x3bc32a48,0xb5053bce,0x33c6bbfe,0x3b993303,
0x3b64361f,0xbaf6367c,0x361fbb64,0x37e33b50,0xbb64b61f,0x3a0fb89b,0xb61f3b64,0xb93aba8a,0x3b64361f,0xb8ec39cb,0x361fbb64,0x3a4f3984,
0xbb64b61f,0x3732bac2,0xb61f3b64,0xbb25b848,0x30b2bb88,0x39843b25,0xbbeab564,0x39cbb732,0x33c63bfe,0xbbceb7e3,0x3bc3aa48,0xb3033af6,
0xb8c4bb3b,0x3b77acb5,0xba6d36d7,0xb5c2bbfa,0x3add395f,0xb89b38ec,0x381db9ed,0x3a8a3a4f,0xbbf6b4a5,0x3848b7e3,0x2e463ba8,0xbac2baf6,
0x3913b78b,0x367c3bfa,0xba2fbb0e,0x3b502cb5,0x2e463ba8,0xbbe2b8ec,0x3bf634a5,0xb1793a4f,0xba2fbb0e,0x3984b505,0xb913378b,0xb9cbbb99,
0x35643bc3,0xbb99bac2,0x3b8833c6,0xb5053848,0xbbfeb8c4,0x37e3b5c2,0xaa483a6d,0xbaf6bb77,0x36d7b81d,0x3a0f3be2,0xbb3bbadd,0x393ab179,
0x395f3bea,0xba4fa648,0x39edb0b2,0x38ec3bff,0x3aa7323e,0xacb5389b,0xb872bbd9,0x3bfa3a8a,0x38723bd9,0xbbf1b984,0x3aa7323e,0x2fd639cb,
0xbaa7b23e,0xb505bac2,0x38723bd9,0xbb99b848,0xb872bbd9,0x3af635c2,0xbaa7b23e,0xb7e3bb77,0xb9edbbea,0x3be23a4f,0xb95fb0b2,0xb179b8ec,
0x3564b3c6,0x39843b99,0xbb88bbc3,0x39cb3505,0x3bfe3a6d,0xb3033444,0xaa48b8c4,0x3bce3bb6,0x36d73add,0xbb77b93a,0x3b3b381d,0x35c23a0f,
0xb78bae46,0xb67cb93a,0x3b0e3bf6,0xbb50ba0f,0xbba8ba2f,0x3179afd6,0x34a53913,0xbbe2bbf1,0xbb0ebbf6,0x39843732,0xb78bae46,0xb9cbbb25,
0xb4a5b913,0x3bce3af6,0xbba8ba2f,0xb303b7e3,0x3bc33bfe,0xba4fb9cb,0x33c62a48,0x38ec3984,0x3a6d3b3b,0xbb25bac2,0x38c436d7,0x37323848,
0x381d395f,0xbbb6bb77,0x3add39ed,0x344435c2,0x30b23564,0xbbfabbe2,0x3bea3b88,0x2cb53179,0x3c003c00,0xafd6a648,0,0xbbf1bbff,
0x3c003c00,0xb505b303,0,0xbb99bbce,0x3c003c00,0xb7e3b67c,0,0xbaf6bb50,0x3c003c00,0xb93ab89b,0,0xba0fba8a,
0xbbc3bbfe,0x35c22cb5,0x33c62a48,0x3b773bfa,0xba6dbb3b,0x3a8a38ec,0x38c436d7,0x389b3a4f,0xb81db95f,0x3bff3b99,0x3add39ed,0x26483505,
0xb0b2b564,0x3ac23bb6,0x3bea3b88,0xb848b444,0x3b0e3bf6,0xb89bafd6,0xb78bae46,0xba8abbf1,0x34a53913,0xbbffbb25,0xbba8ba2f,0x2648b732,
0xb78bae46,0xb848baf6,0xbb0ebbf6,0x3ac237e3,0xbba8ba2f,0x367cacb5,0xb4a5b913,0x3b503bfa,0xb9edbbea,0x3a0f3179,0x395f30b2,0x393a3be2,
0x3564b3c6,0x3a4f3bff,0x3b883bc3,0xb8ec2648,0x3bfe3a6d,0xb7323303,0x2a4838c4,0xbb25bbce,0x36d73add,0xbbb6bb50,0xbb3bb81d,0x3444b67c,
0x38723bd9,0xbb25b303,0xbaa7b23e,0xb732bbce,0xbaa7b23e,0xb444bb50,0xb872bbd9,0x3bb6367c,0xb872bbd9,0x3bfa389b,0x3aa7323e,0x2cb53a8a,
0x3aa7323e,0xafd63984,0x38723bd9,0xbbf1b9cb,0xb564bbc3,0x3bce3444,0x3b8833c6,0x33033bb6,0x3bfe38c4,0xb5c2393a,0xaa483a6d,0xbb77ba0f,
0xb6d7381d,0xb89bbbf1,0xbb3bbadd,0x3a8aafd6,0xb95fbbea,0x3bff3732,0x39edb0b2,0x26483b25,0x2e463ba8,0xbbffb505,0xbbf6b4a5,0x2648bb99,
0xba2fbb0e,0x3ac2b444,0x3913b78b,0x38483bb6,0x3bf634a5,0xb67c3a0f,0x2e463ba8,0xbb50b93a,0xb913378b,0xb179bbf1,0xba2fbb0e,0x3be22fd6,
0x30b2bb88,0x3bb635c2,0x3bea3564,0xb4443b77,0x33c63bfe,0xbbfab179,0xbbc32a48,0x2cb5bbe2,0xb8c4bb3b,0x3bf1a648,0x3a6db6d7,0x2fd63bff,
0x3add395f,0xbb993303,0xb81d39ed,0xb505bbce,0xb61f3b64,0xbaf6b67c,0xbb64b61f,0x37e3bb50,0x361fbb64,0x3a0f389b,0x3b64361f,0xb93a3a8a,
0xb61f3b64,0xb8ecb9cb,0xbb64b61f,0x3a4fb984,0x361fbb64,0x37323ac2,0x3b64361f,0xbb253848,0x38c4bb3b,0x39cb3732,0x3a6d36d7,0xb9843b25,
0xbadd395f,0xb303baf6,0xb81db9ed,0x3bceb7e3,0x3beab564,0xb5c23bfa,0x30b23b88,0xbb77acb5,0xbbc3aa48,0x3a8aba4f,0x33c6bbfe,0x389b38ec,
0xba2f3b0e,0xb848b7e3,0xb913b78b,0x3ac2baf6,0x3bf6b4a5,0xb67c3bfa,0xae463ba8,0xbb502cb5,0xb913b78b,0x3be2b8ec,0x3a2fbb0e,0x31793a4f,
0xae463ba8,0xb984b505,0xbbf634a5,0x39cbbb99,0x3b3bbadd,0x35053848,0x36d7381d,0xbb993ac2,0xb9edb0b2,0x3af6bb77,0x395fbbea,0x37e335c2,
0xb5643bc3,0xb93ab179,0xbb8833c6,0x3a0fbbe2,0x3bfeb8c4,0xb8ec3bff,0x2a483a6d,0xba4f2648,0xbbd93aa7,0xacb5b89b,0xb23eb872,0x3bfaba8a,
0x323e3872,0xbbf13984,0xbbd93aa7,0x2fd6b9cb,0x3bd9baa7,0xb5053ac2,0x323e3872,0xbb993848,0xb23eb872,0x3af6b5c2,0x3bd9baa7,0xb7e33b77,
0x3bfeba6d,0xb17938ec,0xaa4838c4,0xbbe23a4f,0x36d7badd,0x39cbb505,0x3b3bb81d,0xb9843b99,0xb95f30b2,0x3bcebbb6,0x39edbbea,0x33033444,
0xbb883bc3,0x35c2ba0f,0xb564b3c6,0x3b77b93a,0xbba83a2f,0x367cb93a,0x34a5b913,0x3b50ba0f,0xbb0e3bf6,0xb179afd6,0xb78b2e46,0x3be2bbf1,
0xb4a53913,0xb9843732,0xbba83a2f,0x39cbbb25,0x378bae46,0xbbce3af6,0xbb0e3bf6,0x3303b7e3,0x3addb9ed,0xb8ec3984,0xb81d395f,0xba4f39cb,
0x3beabb88,0xb7323848,0xb0b23564,0xbb253ac2,0x3bc3bbfe,0xb44435c2,0x33c6aa48,0xbbb63b77,0x3a6dbb3b,0xacb53179,0x38c4b6d7,0xbbfa3be2,
0xb9a839a8,0x3a4fb9cb,0x39a8b9a8,0x38ecb984,0xb9a839a8,0x3b25bac2,0x39a8b9a8,0x3732b848,0xb9a839a8,0x3bb6bb77,0x39a8b9a8,0x3444b5c2,
0xb9a839a8,0x3bfabbe2,0x39a8b9a8,0x2cb5b179,0x381db95f,0xbb503a0f,0xbadd39ed,0xb67c393a,0x30b2b564,0xbbe23bf1,0xbbea3b88,0x31792fd6,
0xb3c62a48,0xb9cb3b25,0xbbc33bfe,0x3984b732,0xb8c436d7,0xb30337e3,0xba6d3b3b,0x3bcebaf6,0xb4a53913,0x3be2ba4f,0x3ba8ba2f,0x3179b8ec,
0x378bae46,0x3984bb99,0x3b0ebbf6,0xb9cb3505,0x3ba8ba2f,0xb303b444,0x34a5b913,0xbbce3bb6,0x3b0ebbf6,0xbb77393a,0xb78b2e46,0xb5c23a0f,
0x2a48b8c4,0xbbfa3a8a,0xbbfe3a6d,0x2cb5389b,0xbb3b381d,0xafd639cb,0xb6d73add,0x3bf1b984,0xb9ed3bea,0x3b99b848,0x395fb0b2,0x3505bac2,
0x356433c6,0x37e3bb77,0x3b88bbc3,0xbaf635c2,0x323e3872,0x3b99bac2,0x3bd9baa7,0xb505b848,0x3bd9baa7,0xb7e3b5c2,0xb23eb872,0xbaf63b77,
0xb23eb872,0xba0f3be2,0xbbd93aa7,0x393a3179,0xbbd93aa7,0x3a4fa648,0x323e3872,0x38ecbbff,0xb6d7b81d,0xbac23af6,0xbb3b3add,0x384837e3,
0xb95f3bea,0x3b50acb5,0x39ed30b2,0x367cbbfa,0x3b88b3c6,0xb179ba4f,0x3564bbc3,0xbbe238ec,0xaa48ba6d,0xb9cb3b99,0xbbfe38c4,0x39843505,
0x3913378b,0x3984bb25,0x3a2fbb0e,0xb9cbb732,0x2e46bba8,0xbbce37e3,0xbbf634a5,0x33033af6,0xba2f3b0e,0x3b772cb5,0x3913378b,0x35c2bbfa,
0x3bf6b4a5,0xb89bb8ec,0x2e46bba8,0xba8a3a4f,0xba6db6d7,0xb7e33b50,0xb8c43b3b,0x3af6367c,0x381d39ed,0x393aba8a,0x3addb95f,0xba0fb89b,
0xb0b2bb88,0xba4f3984,0xbbea3564,0x38ec39cb,0xb3c63bfe,0x3b25b848,0x3bc32a48,0xb732bac2,0x3b64361f,0x3444bb77,0x361fbb64,0xbbb6b5c2,
0xbb64b61f,0xacb53be2,0xb61f3b64,0x3bfa3179,0x3b64361f,0xafd6bbff,0x361fbb64,0xbbf12648,0xbb64b61f,0x35053bce,0xb61f3b64,0x3b99b303,
0xbbeab564,0xa6483b99,0xb0b23b88,0x3bff3505,0x3bc3aa48,0xb848bbb6,0xb3c6bbfe,0xbac23444,0xba6d36d7,0x3b50393a,0x38c43b3b,0x367cba0f,
0x381db9ed,0xbbe2afd6,0xbaddb95f,0x31793bf1,0x3bf634a5,0xb303bbb6,0xae46bba8,0xbbceb444,0xb913378b,0x3b773a0f,0x3a2f3b0e,0x35c2b93a,
0xae46bba8,0xba8a2fd6,0xbbf6b4a5,0x389b3bf1,0x3a2f3b0e,0xa648bb25,0x3913b78b,0xbbffb732,0xbb88b3c6,0x37323bce,0x35643bc3,0x3b253303,
0x2a48ba6d,0xbbb6b67c,0xbbfeb8c4,0x34443b50,0x3b3b3add,0xacb5ba8a,0x36d7b81d,0xbbfab89b,0xb9ed30b2,0x3bf139cb,0x395f3bea,0x2fd6b984,
0x3aa7323e,0xb93abbe2,0xb872bbd9,0xba0fb179,0x38723bd9,0x38eca648,0x3aa7323e,0xba4fbbff,0xbaa7b23e,0x3b253bce,0x38723bd9,0x3732b303,
0xb872bbd9,0xb444367c,0xbaa7b23e,0x3bb63b50,0xb95fb0b2,0x3a8a3bf1,0x39ed3bea,0x389b2fd6,0xbb88bbc3,0xa6483732,0xb56433c6,0x3bff3b25,
0xaa48b8c4,0xbac2b7e3,0xbbfeba6d,0x38483af6,0x3b3b381d,0xbb50bbfa,0xb6d7badd,0xb67c2cb5,0x378b2e46,0xbb77bbfa,0xbb0ebbf6,0xb5c2acb5,
0x3ba83a2f,0xb89bba4f,0xb4a5b913,0xba8ab8ec,0x3b0e3bf6,0xa648b505,0x378b2e46,0xbbffbb99,0x34a53913,0x38483444,0x3ba83a2f,0xbac2bbb6,
0xb3c6aa48,0x3bf13bff,0x3bc33bfe,0x2fd62648,0xb8c4b6d7,0x3b993bce,0x3a6d3b3b,0x35053303,0xbaddb9ed,0x3af63b50,0x381d395f,0x37e3367c,
0xbbeabb88,0x3a0f3a8a,0x30b23564,0x393a389b,0x3c003c00,0x2fd62648,0,0x3bf13bff,0x3c003c00,0x35053303,0,0x3b993bce,
0x3c003c00,0x37e3367c,0,0x3af63b50,0x3c003c00,0x393a389b,0,0x3a0f3a8a,0xbbc3bbfe,0xb5c2acb5,0x33c62a48,0xbb77bbfa,
0xba6dbb3b,0xba8ab8ec,0x38c436d7,0xb89bba4f,0xb81db95f,0xbbffbb99,0x3add39ed,0xa648b505,0xb0b2b564,0xbac2bbb6,0x3bea3b88,0x38483444,
0x3b0e3bf6,0x389b2fd6,0xb78bae46,0x3a8a3bf1,0x34a53913,0x3bff3b25,0xbba8ba2f,0xa6483732,0xb78bae46,0x38483af6,0xbb0ebbf6,0xbac2b7e3,
0xbba8ba2f,0xb67c2cb5,0xb4a5b913,0xbb50bbfa,0xb9edbbea,0xba0fb179,0x395f30b2,0xb93abbe2,0x3564b3c6,0xba4fbbff,0x3b883bc3,0x38eca648,
0x3bfe3a6d,0x3732b303,0x2a4838c4,0x3b253bce,0x36d73add,0x3bb63b50,0xbb3bb81d,0xb444367c,0x38723bd9,0x3b253303,0xbaa7b23e,0x37323bce,
0xbaa7b23e,0x34443b50,0xb872bbd9,0xbbb6b67c,0xb872bbd9,0xbbfab89b,0x3aa7323e,0xacb5ba8a,0x3aa7323e,0x2fd6b984,0x38723bd9,0x3bf139cb,
0xb564bbc3,0xbbceb444,0x3b8833c6,0xb303bbb6,0x3bfe38c4,0x35c2b93a,0xaa483a6d,0x3b773a0f,0xb6d7381d,0x389b3bf1,0xbb3bbadd,0xba8a2fd6,
0xb95fbbea,0xbbffb732,0x39edb0b2,0xa648bb25,0x2e463ba8,0x3bff3505,0xbbf6b4a5,0xa6483b99,0xba2fbb0e,0xbac23444,0x3913b78b,0xb848bbb6,
0x3bf634a5,0x367cba0f,0x2e463ba8,0x3b50393a,0xb913378b,0x31793bf1,0xba2fbb0e,0xbbe2afd6,0x30b2bb88,0xbbb6b5c2,0x3bea3564,0x3444bb77,
0x33c63bfe,0x3bfa3179,0xbbc32a48,0xacb53be2,0xb8c4bb3b,0xbbf12648,0x3a6db6d7,0xafd6bbff,0x3add395f,0x3b99b303,0xb81d39ed,0x35053bce,
0xb61f3b64,0x3af6367c,0xbb64b61f,0xb7e33b50,0x361fbb64,0xba0fb89b,0x3b64361f,0x393aba8a,0xb61f3b64,0x38ec39cb,0xbb64b61f,0xba4f3984,
0x361fbb64,0xb732bac2,0x3b64361f,0x3b25b848,0x38c4bb3b,0xb9cbb732,0x3a6d36d7,0x3984bb25,0xbadd395f,0x33033af6,0xb81db9ed,0xbbce37e3,
0x3beab564,0x35c2bbfa,0x30b23b88,0x3b772cb5,0xbbc3aa48,0xba8a3a4f,0x33c6bbfe,0xb89bb8ec,0xba2f3b0e,0x384837e3,0xb913b78b,0xbac23af6,
0x3bf6b4a5,0x367cbbfa,0xae463ba8,0x3b50acb5,0xb913b78b,0xbbe238ec,0x3a2fbb0e,0xb179ba4f,0xae463ba8,0x39843505,0xbbf634a5,0xb9cb3b99,
0x3b3bbadd,0xb505b848,0x36d7381d,0x3b99bac2,0xb9edb0b2,0xbaf63b77,0x395fbbea,0xb7e3b5c2,0xb5643bc3,0x393a3179,0xbb8833c6,0xba0f3be2,
0x3bfeb8c4,0x38ecbbff,0x2a483a6d,0x3a4fa648,0xbbd93aa7,0x2cb5389b,0xb23eb872,0xbbfa3a8a,0x323e3872,0x3bf1b984,0xbbd93aa7,0xafd639cb,
0x3bd9baa7,0x3505bac2,0x323e3872,0x3b99b848,0xb23eb872,0xbaf635c2,0x3bd9baa7,0x37e3bb77,0x3bfeba6d,0x3179b8ec,0xaa4838c4,0x3be2ba4f,
0x36d7badd,0xb9cb3505,0x3b3bb81d,0x3984bb99,0xb95f30b2,0xbbce3bb6,0x39edbbea,0xb303b444,0xbb883bc3,0xb5c23a0f,0xb564b3c6,0xbb77393a,
0xbba83a2f,0xb67c393a,0x34a5b913,0xbb503a0f,0xbb0e3bf6,0x31792fd6,0xb78b2e46,0xbbe23bf1,0xb4a53913,0x3984b732,0xbba83a2f,0xb9cb3b25,
0x378bae46,0x3bcebaf6,0xbb0e3bf6,0xb30337e3,0x3addb9ed,0x38ecb984,0xb81d395f,0x3a4fb9cb,0x3beabb88,0x3732b848,0xb0b23564,0x3b25bac2,
0x3bc3bbfe,0x3444b5c2,0x33c6aa48,0x3bb6bb77,0x3a6dbb3b,0x2cb5b179,0x38c4b6d7,0x3bfabbe2,0xb9a839a8,0xba4f39cb,0x39a8b9a8,0xb8ec3984,
0xb9a839a8,0xbb253ac2,0x39a8b9a8,0xb7323848,0xb9a839a8,0xbbb63b77,0x39a8b9a8,0xb44435c2,0xb9a839a8,0xbbfa3be2,0x39a8b9a8,0xacb53179,
0x381db95f,0x3b50ba0f,0xbadd39ed,0x367cb93a,0x30b2b564,0x3be2bbf1,0xbbea3b88,0xb179afd6,0xb3c62a48,0x39cbbb25,0xbbc33bfe,0xb9843732,
0xb8c436d7,0x3303b7e3,0xba6d3b3b,0xbbce3af6,0xb4a53913,0xbbe23a4f,0x3ba8ba2f,0xb17938ec,0x378bae46,0xb9843b99,0x3b0ebbf6,0x39cbb505,
0x3ba8ba2f,0x33033444,0x34a5b913,0x3bcebbb6,0x3b0ebbf6,0x3b77b93a,0xb78b2e46,0x35c2ba0f,0x2a48b8c4,0x3bfaba8a,0xbbfe3a6d,0xacb5b89b,
0xbb3b381d,0x2fd6b9cb,0xb6d73add,0xbbf13984,0xb9ed3bea,0xbb993848,0x395fb0b2,0xb5053ac2,0x356433c6,0xb7e33b77,0x3b88bbc3,0x3af6b5c2,
0x323e3872,0xbb993ac2,0x3bd9baa7,0x35053848,0x3bd9baa7,0x37e335c2,0xb23eb872,0x3af6bb77,0xb23eb872,0x3a0fbbe2,0xbbd93aa7,0xb93ab179,
0xbbd93aa7,0xba4f2648,0x323e3872,0xb8ec3bff,0xb6d7b81d,0x3ac2baf6,0xbb3b3add,0xb848b7e3,0xb95f3bea,0xbb502cb5,0x39ed30b2,0xb67c3bfa,
0x3b88b3c6,0x31793a4f,0x3564bbc3,0x3be2b8ec,0xaa48ba6d,0x39cbbb99,0xbbfe38c4,0xb984b505,0x3913378b,0xb9843b25,0x3a2fbb0e,0x39cb3732,
0x2e46bba8,0x3bceb7e3,0xbbf634a5,0xb303baf6,0xba2f3b0e,0xbb77acb5,0x3913378b,0xb5c23bfa,0x3bf6b4a5,0x389b38ec,0x2e46bba8,0x3a8aba4f,
0xba6db6d7,0x37e3bb50,0xb8c43b3b,0xbaf6b67c,0x381d39ed,0xb93a3a8a,0x3addb95f,0x3a0f389b,0xb0b2bb88,0x3a4fb984,0xbbea3564,0xb8ecb9cb,
0xb3c63bfe,0xbb253848,0x3bc32a48,0x37323ac2,0x3b64361f,0xb4443b77,0x361fbb64,0x3bb635c2,0xbb64b61f,0x2cb5bbe2,0xb61f3b64,0xbbfab179,
0x3b64361f,0x2fd63bff,0x361fbb64,0x3bf1a648,0xbb64b61f,0xb505bbce,0xb61f3b64,0xbb993303,0xbbeab564,0x2648bb99,0xb0b23b88,0xbbffb505,
0x3bc3aa48,0x38483bb6,0xb3c6bbfe,0x3ac2b444,0xba6d36d7,0xbb50b93a,0x38c43b3b,0xb67c3a0f,0x381db9ed,0x3be22fd6,0xbaddb95f,0xb179bbf1,
0x3bf634a5,0x33033bb6,0xae46bba8,0x3bce3444,0xb913378b,0xbb77ba0f,0x3a2f3b0e,0xb5c2393a,0xae46bba8,0x3a8aafd6,0xbbf6b4a5,0xb89bbbf1,
0x3a2f3b0e,0x26483b25,0x3913b78b,0x3bff3732,0xbb88b3c6,0xb732bbce,0x35643bc3,0xbb25b303,0x2a48ba6d,0x3bb6367c,0xbbfeb8c4,0xb444bb50,
0x3b3b3add,0x2cb53a8a,0x36d7b81d,0x3bfa389b,0xb9ed30b2,0xbbf1b9cb,0x395f3bea,0xafd63984,0x3aa7323e,0x393a3be2,0xb872bbd9,0x3a0f3179,
0x38723bd9,0xb8ec2648,0x3aa7323e,0x3a4f3bff,0xbaa7b23e,0xbb25bbce,0x38723bd9,0xb7323303,0xb872bbd9,0x3444b67c,0xbaa7b23e,0xbbb6bb50,
0xb95fb0b2,0xba8abbf1,0x39ed3bea,0xb89bafd6,0xbb88bbc3,0x2648b732,0xb56433c6,0xbbffbb25,0xaa48b8c4,0x3ac237e3,0xbbfeba6d,0xb848baf6,
0x3b3b381d,0x3b503bfa,0xb6d7badd,0x367cacb5,0x378b2e46,0x3b773bfa,0xbb0ebbf6,0x35c22cb5,0x3ba83a2f,0x389b3a4f,0xb4a5b913,0x3a8a38ec,
0x3b0e3bf6,0x26483505,0x378b2e46,0x3bff3b99,0x34a53913,0xb848b444,0x3ba83a2f,0x3ac23bb6,0xb3c6aa48,0xbbf1bbff,0x3bc33bfe,0xafd6a648,
0xb8c4b6d7,0xbb99bbce,0x3a6d3b3b,0xb505b303,0xbaddb9ed,0xbaf6bb50,0x381d395f,0xb7e3b67c,0xbbeabb88,0xba0fba8a,0x30b23564,0xb93ab89b,
0x3c003c00,0xba4fb9cb,0,0xb8ecb984,0x3c003c00,0xbb25bac2,0,0xb732b848,0x3c003c00,0xbbb6bb77,0,0xb444b5c2,
0x3c003c00,0xbbfabbe2,0,0xacb5b179,0x33c62a48,0x367c393a,0x3bc33bfe,0xbb50ba0f,0x38c436d7,0xb1792fd6,0x3a6d3b3b,0xbbe2bbf1,
0x3add39ed,0xb984b732,0x381d395f,0xb9cbbb25,0x3bea3b88,0xbbcebaf6,0x30b23564,0xb303b7e3,0xbb0ebbf6,0x3be23a4f,0x378b2e46,0x317938ec,
0xb4a5b913,0x39843b99,0x3ba83a2f,0xb9cbb505,0x378b2e46,0xb3033444,0x3b0e3bf6,0xbbcebbb6,0x3ba83a2f,0xbb77b93a,0x34a53913,0xb5c2ba0f,
0xb95fb0b2,0x2cb5b89b,0xb9edbbea,0x3bfa3a8a,0xbb88bbc3,0x3bf13984,0x3564b3c6,0x2fd639cb,0xaa48b8c4,0x35053ac2,0x3bfe3a6d,0xbb99b848,
0x3b3b381d,0xbaf6b5c2,0x36d73add,0xb7e3bb77,0x38723bd9,0xbb99bac2,0xbaa7b23e,0x3505b848,0xbaa7b23e,0x37e3b5c2,0xb872bbd9,0x3af63b77,
0xb872bbd9,0x3a0f3be2,0x3aa7323e,0xb93a3179,0x3aa7323e,0xba4fa648,0x38723bd9,0xb8ecbbff,0x3b8833c6,0xb84837e3,0x35643bc3,0xbac2baf6,
0xaa483a6d,0xb67cbbfa,0xbbfeb8c4,0x3b502cb5,0xbb3bbadd,0x3be238ec,0x36d7b81d,0xb1793a4f,0x39edb0b2,0xb9843505,0x395f3bea,0xb9cbbb99,
0xae46bba8,0x39843b25,0x3bf634a5,0xb9cb3732,0x3a2f3b0e,0xbbceb7e3,0xb913378b,0x3303baf6,0xbbf6b4a5,0x3b77acb5,0xae46bba8,0x35c23bfa,
0x3913b78b,0xb89b38ec,0x3a2f3b0e,0xba8aba4f,0xbbeab564,0x3af6b67c,0x30b2bb88,0x37e33b50,0x3bc3aa48,0xba0f389b,0x33c63bfe,0xb93aba8a,
0xba6d36d7,0x38ecb9cb,0xb8c4bb3b,0x3a4f3984,0x381db9ed,0xb7323ac2,0x3add395f,0xbb25b848,0xb61f3b64,0xb444bb77,0xbb64b61f,0x3bb6b5c2,
0x361fbb64,0x2cb53be2,0x3b64361f,0xbbfa3179,0xb61f3b64,0x2fd6bbff,0xbb64b61f,0x3bf12648,0x361fbb64,0xb5053bce,0x3b64361f,0xbb99b303,
0x3a6d36d7,0xbbff3505,0xb8c43b3b,0xa648bb99,0xb81db9ed,0x3ac23444,0x3addb95f,0xb8483bb6,0x30b23b88,0xb67cba0f,0xbbea3564,0x3b50b93a,
0x33c6bbfe,0xb1793bf1,0x3bc32a48,0xbbe22fd6,0x3a2fbb0e,0xb3033bb6,0x3913378b,0xbbce3444,0xbbf634a5,0x3b77ba0f,0x2e46bba8,0x35c2393a,
0x3913378b,0xba8aafd6,0xba2f3b0e,0x389bbbf1,0x2e46bba8,0xa6483b25,0x3bf6b4a5,0xbbff3732,0xb6d7b81d,0x3b25b303,0x3b3bbadd,0xb7323bce,
0xb95f3bea,0x3444bb50,0xb9edb0b2,0x3bb6b67c,0x3b88b3c6,0xbbfa389b,0xb5643bc3,0x2cb5ba8a,0xaa48ba6d,0x2fd63984,0x3bfeb8c4,0xbbf139cb,
0xbbd93aa7,0x393abbe2,0xb23eb872,0x3a0fb179,0x323e3872,0xb8eca648,0xbbd93aa7,0x3a4fbbff,0x3bd9baa7,0xbb253bce,0x323e3872,0xb732b303,
0xb23eb872,0x3444367c,0x3bd9baa7,0xbbb63b50,0xaa4838c4,0xb89b2fd6,0xbbfe3a6d,0x3a8abbf1,0x3b3bb81d,0xbbff3b25,0xb6d73add,0xa648b732,
0x39edbbea,0xb8483af6,0x395fb0b2,0xbac237e3,0xb564b3c6,0x367c2cb5,0x3b88bbc3,0xbb503bfa,0x3ba8ba2f,0xbb773bfa,0xb4a53913,0xb5c22cb5,
0x3b0ebbf6,0xb89b3a4f,0x378bae46,0xba8a38ec,0x34a5b913,0xa6483505,0x3ba8ba2f,0xbbff3b99,0xb78b2e46,0x3848b444,0x3b0ebbf6,0xbac23bb6,
0x381db95f,0x2fd6a648,0x3addb9ed,0xbbf13bff,0x30b2b564,0x3505b303,0x3beabb88,0xbb993bce,0xb3c62a48,0x37e3b67c,0x3bc3bbfe,0xbaf63b50,
0xb8c436d7,0x393ab89b,0x3a6dbb3b,0xba0f3a8a,0xb9a839a8,0x3bf1bbff,0x39a8b9a8,0xafd62648,0xb9a839a8,0x3b99bbce,0x39a8b9a8,0xb5053303,
0xb9a839a8,0x3af6bb50,0x39a8b9a8,0xb7e3367c,0xb9a839a8,0x3a0fba8a,0x39a8b9a8,0xb93a389b,0xbadd39ed,0x35c2acb5,0xb81d395f,0x3b77bbfa,
0xbbea3b88,0x3a8ab8ec,0xb0b23564,0x389bba4f,0xbbc33bfe,0x3bffbb99,0x33c6aa48,0x2648b505,0xba6d3b3b,0x3ac2bbb6,0x38c4b6d7,0xb8483444,
0x34a5b913,0xba8a3bf1,0xbba83a2f,0x389bafd6,0xb78b2e46,0x26483732,0xbb0e3bf6,0x3bffbb25,0xbba83a2f,0x3ac2b7e3,0xb4a53913,0x3848baf6,
0xbb0e3bf6,0x3b50bbfa,0x378bae46,0xb67cacb5,0x3bfeba6d,0xba0f3179,0x2a48b8c4,0xb93a3be2,0x36d7badd,0xba4f3bff,0xbb3b381d,0x38ec2648,
0xb95f30b2,0x37323303,0xb9ed3bea,0x3b25bbce,0xbb883bc3,0x3bb6bb50,0x356433c6,0xb444b67c,0x323e3872,0x3732bbce,0x3bd9baa7,0xbb253303,
0x3bd9baa7,0xbbb6367c,0xb23eb872,0xb4443b50,0xb23eb872,0xacb53a8a,0xbbd93aa7,0x3bfab89b,0xbbd93aa7,0x3bf1b9cb,0x323e3872,0xafd6b984,
0xbb3b3add,0x3bceb444,0x36d7381d,0x3303bbb6,0x39ed30b2,0xb5c2b93a,0x395fbbea,0xbb773a0f,0x3564bbc3,0xb89b3bf1,0xbb8833c6,0x3a8a2fd6,
0xbbfe38c4,0x3bffb732,0x2a483a6d,0x2648bb25,0xb913b78b,0x26483b99,0xba2f3b0e,0x3bffb505,0xae463ba8,0x3848bbb6,0x3bf6b4a5,0xbac2b444,
0x3a2fbb0e,0xbb50393a,0xb913b78b,0x367c3a0f,0xbbf634a5,0x3be2afd6,0xae463ba8,0x3179bbf1,0x38c4bb3b,0xbbb635c2,0xba6db6d7,0x34443b77,
0xbadd395f,0x3bfab179,0x381d39ed,0xacb5bbe2,0x3beab564,0xbbf1a648,0xb0b2bb88,0xafd63bff,0xbbc3aa48,0x3b993303,0xb3c63bfe,0x3505bbce,
0x3b64361f,0xb7e3bb50,0x361fbb64,0xbaf6367c,0xbb64b61f,0x393a3a8a,0xb61f3b64,0x3a0fb89b,0x3b64361f,0xba4fb984,0x361fbb64,0xb8ec39cb,
0xbb64b61f,0x3b253848,0xb61f3b64,0x3732bac2,0xb0b23b88,0x39cbb732,0x3bea3564,0xb984bb25,0xb3c6bbfe,0xb3033af6,0xbbc32a48,0x3bce37e3,
0x38c43b3b,0xb5c2bbfa,0x3a6db6d7,0xbb772cb5,0xbaddb95f,0x3a8a3a4f,0xb81d39ed,0x389bb8ec,0xbbf6b4a5,0x3ac23af6,0x2e463ba8,0x3848b7e3,
0x3913b78b,0xbb50acb5,0xba2fbb0e,0x367c3bfa,0x2e463ba8,0x3179ba4f,0x3bf634a5,0xbbe2b8ec,0xba2fbb0e,0x39cb3b99,0xb913378b,0x3984b505,
0xb564bbc3,0xb5053848,0xbb88b3c6,0x3b993ac2,0x3bfe38c4,0xbaf6bb77,0x2a48ba6d,0xb7e335c2,0xb6d7381d,0x393ab179,0x3b3b3add,0xba0fbbe2,
0xb95fbbea,0x38ec3bff,0xb9ed30b2,0x3a4f2648,0x3aa7323e,0xbbfaba8a,0xb872bbd9,0xacb5389b,0x38723bd9,0xafd6b9cb,0x3aa7323e,0xbbf1b984,
0xbaa7b23e,0x3b993848,0x38723bd9,0xb505bac2,0xb872bbd9,0x37e33b77,0xbaa7b23e,0x3af635c2,0x39ed3bea,0xb179b8ec,0x395f30b2,0xbbe2ba4f,
0xb56433c6,0x39cb3505,0x3b883bc3,0xb984bb99,0xbbfeba6d,0x3bce3bb6,0x2a4838c4,0x3303b444,0xb6d7badd,0x35c23a0f,0xbb3bb81d,0x3b77393a,
0xb78bae46,0x3b503a0f,0x3b0e3bf6,0xb67cb93a,0xbba8ba2f,0x3be23bf1,0x34a53913,0x3179afd6,0xbb0ebbf6,0x39cb3b25,0xb78bae46,0x39843732,
0xb4a5b913,0x330337e3,0xbba8ba2f,0x3bce3af6,0xbbc3bbfe,0x38ec3984,0xb3c6aa48,0x3a4f39cb,0xba6dbb3b,0x37323848,0xb8c4b6d7,0x3b253ac2,
0xb81db95f,0x344435c2,0xbaddb9ed,0x3bb63b77,0xb0b2b564,0x2cb53179,0xbbeabb88,0x3bfa3be2,0x3c003c00,0x3a4f39cb,0,0x38ec3984,
0x3c003c00,0x3b253ac2,0,0x37323848,0x3c003c00,0x3bb63b77,0,0x344435c2,0x3c003c00,0x3bfa3be2,0,0x2cb53179,
0x33c62a48,0xb67cb93a,0x3bc33bfe,0x3b503a0f,0x38c436d7,0x3179afd6,0x3a6d3b3b,0x3be23bf1,0x3add39ed,0x39843732,0x381d395f,0x39cb3b25,
0x3bea3b88,0x3bce3af6,0x30b23564,0x330337e3,0xbb0ebbf6,0xbbe2ba4f,0x378b2e46,0xb179b8ec,0xb4a5b913,0xb984bb99,0x3ba83a2f,0x39cb3505,
0x378b2e46,0x3303b444,0x3b0e3bf6,0x3bce3bb6,0x3ba83a2f,0x3b77393a,0x34a53913,0x35c23a0f,0xb95fb0b2,0xacb5389b,0xb9edbbea,0xbbfaba8a,
0xbb88bbc3,0xbbf1b984,0x3564b3c6,0xafd6b9cb,0xaa48b8c4,0xb505bac2,0x3bfe3a6d,0x3b993848,0x3b3b381d,0x3af635c2,0x36d73add,0x37e33b77,
0x38723bd9,0x3b993ac2,0xbaa7b23e,0xb5053848,0xbaa7b23e,0xb7e335c2,0xb872bbd9,0xbaf6bb77,0xb872bbd9,0xba0fbbe2,0x3aa7323e,0x393ab179,
0x3aa7323e,0x3a4f2648,0x38723bd9,0x38ec3bff,0x3b8833c6,0x3848b7e3,0x35643bc3,0x3ac23af6,0xaa483a6d,0x367c3bfa,0xbbfeb8c4,0xbb50acb5,
0xbb3bbadd,0xbbe2b8ec,0x36d7b81d,0x3179ba4f,0x39edb0b2,0x3984b505,0x395f3bea,0x39cb3b99,0xae46bba8,0xb984bb25,0x3bf634a5,0x39cbb732,
0x3a2f3b0e,0x3bce37e3,0xb913378b,0xb3033af6,0xbbf6b4a5,0xbb772cb5,0xae46bba8,0xb5c2bbfa,0x3913b78b,0x389bb8ec,0x3a2f3b0e,0x3a8a3a4f,
0xbbeab564,0xbaf6367c,0x30b2bb88,0xb7e3bb50,0x3bc3aa48,0x3a0fb89b,0x33c63bfe,0x393a3a8a,0xba6d36d7,0xb8ec39cb,0xb8c4bb3b,0xba4fb984,
0x381db9ed,0x3732bac2,0x3add395f,0x3b253848,0xb61f3b64,0x34443b77,0xbb64b61f,0xbbb635c2,0x361fbb64,0xacb5bbe2,0x3b64361f,0x3bfab179,
0xb61f3b64,0xafd63bff,0xbb64b61f,0xbbf1a648,0x361fbb64,0x3505bbce,0x3b64361f,0x3b993303,0x3a6d36d7,0x3bffb505,0xb8c43b3b,0x26483b99,
0xb81db9ed,0xbac2b444,0x3addb95f,0x3848bbb6,0x30b23b88,0x367c3a0f,0xbbea3564,0xbb50393a,0x33c6bbfe,0x3179bbf1,0x3bc32a48,0x3be2afd6,
0x3a2fbb0e,0x3303bbb6,0x3913378b,0x3bceb444,0xbbf634a5,0xbb773a0f,0x2e46bba8,0xb5c2b93a,0x3913378b,0x3a8a2fd6,0xba2f3b0e,0xb89b3bf1,
0x2e46bba8,0x2648bb25,0x3bf6b4a5,0x3bffb732,0xb6d7b81d,0xbb253303,0x3b3bbadd,0x3732bbce,0xb95f3bea,0xb4443b50,0xb9edb0b2,0xbbb6367c,
0x3b88b3c6,0x3bfab89b,0xb5643bc3,0xacb53a8a,0xaa48ba6d,0xafd6b984,0x3bfeb8c4,0x3bf1b9cb,0xbbd93aa7,0xb93a3be2,0xb23eb872,0xba0f3179,
0x323e3872,0x38ec2648,0xbbd93aa7,0xba4f3bff,0x3bd9baa7,0x3b25bbce,0x323e3872,0x37323303,0xb23eb872,0xb444b67c,0x3bd9baa7,0x3bb6bb50,
0xaa4838c4,0x389bafd6,0xbbfe3a6d,0xba8a3bf1,0x3b3bb81d,0x3bffbb25,0xb6d73add,0x26483732,0x39edbbea,0x3848baf6,0x395fb0b2,0x3ac2b7e3,
0xb564b3c6,0xb67cacb5,0x3b88bbc3,0x3b50bbfa,0x3ba8ba2f,0x3b77bbfa,0xb4a53913,0x35c2acb5,0x3b0ebbf6,0x389bba4f,0x378bae46,0x3a8ab8ec,
0x34a5b913,0x2648b505,0x3ba8ba2f,0x3bffbb99,0xb78b2e46,0xb8483444,0x3b0ebbf6,0x3ac2bbb6,0x381db95f,0xafd62648,0x3addb9ed,0x3bf1bbff,
0x30b2b564,0xb5053303,0x3beabb88,0x3b99bbce,0xb3c62a48,0xb7e3367c,0x3bc3bbfe,0x3af6bb50,0xb8c436d7,0xb93a389b,0x3a6dbb3b,0x3a0fba8a,
0xb9a839a8,0xbbf13bff,0x39a8b9a8,0x2fd6a648,0xb9a839a8,0xbb993bce,0x39a8b9a8,0x3505b303,0xb9a839a8,0xbaf63b50,0x39a8b9a8,0x37e3b67c,
0xb9a839a8,0xba0f3a8a,0x39a8b9a8,0x393ab89b,0xbadd39ed,0xb5c22cb5,0xb81d395f,0xbb773bfa,0xbbea3b88,0xba8a38ec,0xb0b23564,0xb89b3a4f,
0xbbc33bfe,0xbbff3b99,0x33c6aa48,0xa6483505,0xba6d3b3b,0xbac23bb6,0x38c4b6d7,0x3848b444,0x34a5b913,0x3a8abbf1,0xbba83a2f,0xb89b2fd6,
0xb78b2e46,0xa648b732,0xbb0e3bf6,0xbbff3b25,0xbba83a2f,0xbac237e3,0xb4a53913,0xb8483af6,0xbb0e3bf6,0xbb503bfa,0x378bae46,0x367c2cb5,
0x3bfeba6d,0x3a0fb179,0x2a48b8c4,0x393abbe2,0x36d7badd,0x3a4fbbff,0xbb3b381d,0xb8eca648,0xb95f30b2,0xb732b303,0xb9ed3bea,0xbb253bce,
0xbb883bc3,0xbbb63b50,0x356433c6,0x3444367c,0x323e3872,0xb7323bce,0x3bd9baa7,0x3b25b303,0x3bd9baa7,0x3bb6b67c,0xb23eb872,0x3444bb50,
0xb23eb872,0x2cb5ba8a,0xbbd93aa7,0xbbfa389b,0xbbd93aa7,0xbbf139cb,0x323e3872,0x2fd63984,0xbb3b3add,0xbbce3444,0x36d7381d,0xb3033bb6,
0x39ed30b2,0x35c2393a,0x395fbbea,0x3b77ba0f,0x3564bbc3,0x389bbbf1,0xbb8833c6,0xba8aafd6,0xbbfe38c4,0xbbff3732,0x2a483a6d,0xa6483b25,
0xb913b78b,0xa648bb99,0xba2f3b0e,0xbbff3505,0xae463ba8,0xb8483bb6,0x3bf6b4a5,0x3ac23444,0x3a2fbb0e,0x3b50b93a,0xb913b78b,0xb67cba0f,
0xbbf634a5,0xbbe22fd6,0xae463ba8,0xb1793bf1,0x38c4bb3b,0x3bb6b5c2,0xba6db6d7,0xb444bb77,0xbadd395f,0xbbfa3179,0x381d39ed,0x2cb53be2,
0x3beab564,0x3bf12648,0xb0b2bb88,0x2fd6bbff,0xbbc3aa48,0xbb99b303,0xb3c63bfe,0xb5053bce,0x3b64361f,0x37e33b50,0x361fbb64,0x3af6b67c,
0xbb64b61f,0xb93aba8a,0xb61f3b64,0xba0f389b,0x3b64361f,0x3a4f3984,0x361fbb64,0x38ecb9cb,0xbb64b61f,0xbb25b848,0xb61f3b64,0xb7323ac2,
0xb0b23b88,0xb9cb3732,0x3bea3564,0x39843b25,0xb3c6bbfe,0x3303baf6,0xbbc32a48,0xbbceb7e3,0x38c43b3b,0x35c23bfa,0x3a6db6d7,0x3b77acb5,
0xbaddb95f,0xba8aba4f,0xb81d39ed,0xb89b38ec,0xbbf6b4a5,0xbac2baf6,0x2e463ba8,0xb84837e3,0x3913b78b,0x3b502cb5,0xba2fbb0e,0xb67cbbfa,
0x2e463ba8,0xb1793a4f,0x3bf634a5,0x3be238ec,0xba2fbb0e,0xb9cbbb99,0xb913378b,0xb9843505,0xb564bbc3,0x3505b848,0xbb88b3c6,0xbb99bac2,
0x3bfe38c4,0x3af63b77,0x2a48ba6d,0x37e3b5c2,0xb6d7381d,0xb93a3179,0x3b3b3add,0x3a0f3be2,0xb95fbbea,0xb8ecbbff,0xb9ed30b2,0xba4fa648,
0x3aa7323e,0x3bfa3a8a,0xb872bbd9,0x2cb5b89b,0x38723bd9,0x2fd639cb,0x3aa7323e,0x3bf13984,0xbaa7b23e,0xbb99b848,0x38723bd9,0x35053ac2,
0xb872bbd9,0xb7e3bb77,0xbaa7b23e,0xbaf6b5c2,0x39ed3bea,0x317938ec,0x395f30b2,0x3be23a4f,0xb56433c6,0xb9cbb505,0x3b883bc3,0x39843b99,
0xbbfeba6d,0xbbcebbb6,0x2a4838c4,0xb3033444,0xb6d7badd,0xb5c2ba0f,0xbb3bb81d,0xbb77b93a,0xb78bae46,0xbb50ba0f,0x3b0e3bf6,0x367c393a,
0xbba8ba2f,0xbbe2bbf1,0x34a53913,0xb1792fd6,0xbb0ebbf6,0xb9cbbb25,0xb78bae46,0xb984b732,0xb4a5b913,0xb303b7e3,0xbba8ba2f,0xbbcebaf6,
0xbbc3bbfe,0xb8ecb984,0xb3c6aa48,0xba4fb9cb,0xba6dbb3b,0xb732b848,0xb8c4b6d7,0xbb25bac2,0xb81db95f,0xb444b5c2,0xbaddb9ed,0xbbb6bb77,
0xb0b2b564,0xacb5b179,0xbbeabb88,0xbbfabbe2,0x3c003c00,0x96480000,0x3c003c00,0xa311a248,0x3c003c00,0x9cb69a48,0x3c003c00,0xa452a3db,
0x3c003c00,0x9fdb9e48,0x3c003c00,0xa51ba4b6,0x3c003c00,0xa17fa0b6,0x3bff3c00,0xa5e4a57f,0x3c003c00,0x9fdb0000,0x3bfb3bfc,0xac6aabd9,
0x3bff3c00,0xa5e4a3db,0x3bf93bfa,0xad65ace7,0x3bfe3bff,0xa8e8a7da,0x3bf63bf7,0xae5fade2,0x3bfd3bfe,0xaadea9e3,0x3bf23bf4,0xaf59aedc,
0x3c003c00,0xa3110000,0x3bf03bf4,0xafefaf0e,0x3bfe3bff,0xa94da711,0x3be83bed,0xb0d7b067,0x3bfb3bfd,0xac6aab11,0x3bdf3be4,0xb1b6b147,
0x3bf63bf9,0xae2dad4c,0x3bd43bda,0xb294b226,0x3c003c00,0xa51b0000,0x3bdf3be6,0xb1b6b115,0x3bfc3bfe,0xaba7a91b,0x3bcf3bd7,0xb2f7b257,
0x3bf63bf9,0xae5fad1a,0x3bbc3bc6,0xb41ab396,0x3bec3bf1,0xb074afa4,0x3ba53bb1,0xb4b7b469,0x3bff3c00,0xa6ad0000,0x3bc83bd4,0xb371b2a1,
0x3bfa3bfd,0xad00aaac,0x3bac3bbb,0xb487b420,0x3bef3bf5,0xb029aeaa,0x3b8b3b9d,0xb552b4ed,0x3bde3be7,0xb1cfb0fd,0x3b653b79,0xb61ab5b6,
0x3bff3c00,0xa81f0000,0x3bab3bbc,0xb493b414,0x3bf63bfc,0xae2dac1f,0x3b813b97,0xb58db511,0x3be53bef,0xb122b01d,0x3b4f3b69,0xb682b608,
0x3bcc3bda,0xb328b226,0x3b163b33,0xb76fb6f9,0x3bfe3c00,0xa8e80000,0x3b873ba0,0xb56ab4d5,0x3bf23bfa,0xaf59ace7,0x3b4c3b6b,0xb68db5fd,
0x3bda3be8,0xb219b0e4,0x3b073b2b,0xb7a6b71b,0x3bb73bca,0xb43eb34c,0x3ab63ae0,0xb85ab817,0x3bfe3c00,0xa9b10000,0x3b5e3b80,0xb63cb593,
0x3bee3bf8,0xb042adb0,0x3b103b39,0xb785b6e3,0x3bce3be0,0xb30fb1aa,0x3ab33ae3,0xb85fb812,0x3b9e3bb7,0xb4e7b438,0x3a493a7f,0xb8f3b8ab,
0x3bfd3c00,0xaa7a0000,0x3b2f3b5a,0xb70ab64e,0x3be83bf6,0xb0d7ae78,0x3acb3aff,0xb83ab7c2,0x3bbf3bd6,0xb402b26f,0x3a543a92,0xb8e5b891,
0x3b813ba2,0xb58db4c9,0x39cd3a13,0xb982b935,0x3bfd3c00,0xab430000,0x3afb3b30,0xb7d2b705,0x3be23bf3,0xb16caf40,0x3a7e3abf,0xb8adb84d,
0x3bae3bcb,0xb47bb334,0x39eb3a37,0xb962b909,0x3b603b8a,0xb631b558,0x3946399b,0xba04b9b5,0x3bfc3c00,0xac060000,0x3ac13b02,0xb84ab7b7,
0x3bdc3bf0,0xb201b004,0x3a293a78,0xb91bb8b5,0x3b9c3bc0,0xb4f3b3f7,0x397939d4,0xb9d6b97b,0x3b3d3b70,0xb6d2b5e5,0x38b23918,0xba7aba2b,
0x3bfb3c00,0xac6a0000,0x3a813ad0,0xb8a8b832,0x3bd43bed,0xb294b067,0x39cd3a2b,0xb982b918,0x3b873bb2,0xb56ab45d,0x38fd3969,0xba41b9e5,
0x3b163b53,0xb76fb670,0x3815388c,0xbae1ba95,0x3bfa3c00,0xacce0000,0x3a3d3a99,0xb902b887,0x3bcc3be9,0xb328b0cb,0x396b39d8,0xb9e3b976,
0x3b713ba4,0xb5dfb4bd,0x387a38f6,0xbaa2ba47,0x3aeb3b33,0xb805b6f9,0x36dd37ee,0xbb3abaf3,0x3bf93c00,0xad330000,0x39f43a5e,0xb958b8d8,
0x3bc33be5,0xb3bab12e,0x39023980,0xba3db9d0,0x3b593b95,0xb654b51d,0x37dd387c,0xbaf7baa0,0x3abd3b11,0xb850b780,0x358136b5,0xbb83bb43,
0x3bf83c00,0xad970000,0x39a63a1f,0xb9aab927,0x3bba3be1,0xb426b191,0x38943922,0xba90ba23,0x3b3f3b84,0xb6c6b57c,0x36bb37f9,0xbb42baf0,
0x3a8c3aed,0xb899b802,0x341a3570,0xbbbcbb86,0x3bf73c00,0xadfb0000,0x395439dc,0xb9f8b972,0x3bb03bdc,0xb46fb1f4,0x382038bf,0xbadbba71,
0x3b243b72,0xb737b5da,0x358d36ee,0xbb81bb36,0x3a583ac6,0xb8e0b842,0x31533420,0xbbe3bbbb,0x3bf63c00,0xae5f0000,0x38fd3996,0xba41b9ba,
0x3ba53bd7,0xb4b7b257,0x374e3858,0xbb1ebab8,0x3b073b5f,0xb7a6b637,0x345735da,0xbbb3bb72,0x3a213a9c,0xb924b881,0x2cce3191,0xbbfabbe1,
0x3bf53c00,0xaec30000,0x38a3394d,0xba85b9fe,0x3b9a3bd2,0xb4ffb2b9,0x365437d8,0xbb59baf9,0x3ae83b4b,0xb80ab693,0x323234bd,0xbbd9bba4,
0x39e73a71,0xb966b8bf,0xa4522db0,0xbc00bbf8,0x3bf33c00,0xaf270000,0x38453900,0xbac4ba3f,0x3b8e3bcd,0xb546b31b,0x355236f9,0xbb8bbb33,
0x3ac73b36,0xb840b6ee,0x2f593334,0xbbf2bbcb,0x39aa3a43,0xb9a6b8fb,0xaef51a48,0xbbf4bc00,0x3bf23c00,0xaf8b0000,0x37c838b0,0xbafeba7c,
0x3b813bc7,0xb58db37d,0x344b3614,0xbbb5bb67,0x3aa53b20,0xb874b748,0x288430e4,0xbbffbbe8,0x396b3a13,0xb9e3b935,0xb263ad4c,0xbbd7bbf9,
0x3bf03c00,0xafef0000,0x36ff385d,0xbb32bab5,0x3b733bc1,0xb5d4b3df,0x327c3529,0xbbd6bb93,0x3a813b08,0xb8a8b7a1,0xa9b12d1a,0xbbfebbf9,
0x392939e1,0xba1db96d,0xb49fb160,0xbba9bbe3,0x3bef3c00,0xb0290000,0x36313807,0xbb60bae9,0x3b653bbb,0xb61ab420,0x305b3438,0xbbedbbb7,
0x3a5c3af0,0xb8dbb7f9,0xafef1e48,0xbbf0bc00,0x38e539ad,0xba54b9a4,0xb602b408,0xbb6abbbe,0x3bed3c00,0xb05b0000,0x355e375e,0xbb89bb1a,
0x3b573bb4,0xb65fb451,0x2c6a3288,0xbbfbbbd5,0x3a353ad6,0xb90cb828,0xb27cac51,0xbbd6bbfb,0x389e3976,0xba89b9d8,0xb759b558,0xbb1bbb8a,
0x3beb3c00,0xb08d0000,0x348736aa,0xbbacbb46,0x3b473bad,0xb6a4b481,0x16483099,0xbc00bbeb,0x3a0d3abc,0xb93cb852,0xb47bb080,0xbbaebbec,
0x3855393e,0xbababa0b,0xb850b69e,0xbabdbb49,0x3be93c00,0xb0be0000,0x335935f1,0xbbc9bb6e,0x3b373ba6,0xb6e8b4b1,0xac382d4c,0xbbfcbbf9,
0x39e33aa0,0xb96bb87c,0xb5b1b2d2,0xbb7abbd1,0x380a3905,0xbae8ba3b,0xb8eab7d8,0xba50baf9,0x3be73c00,0xb0f00000,0x319e3534,0xbbe0bb91,
0x3b273b9e,0xb72cb4e1,0xb042257f,0xbbeebc00,0x39b83a83,0xb999b8a6,0xb6ddb48d,0xbb3abbab,0x377a38c9,0xbb13ba69,0xb979b881,0xb9d6ba9c,
0x3be53c00,0xb1220000,0x2fbd3475,0xbbf1bbaf,0x3b163b97,0xb76fb511,0xb263a91b,0xbbd7bbfe,0x398b3a65,0xb9c5b8ce,0xb7feb5ab,0xbaeebb7b,
0x36dd388c,0xbb3aba95,0xb9fcb90e,0xb94fba33,0x3be33c00,0xb1530000,0x2c383365,0xbbfcbbc9,0x3b043b8f,0xb7b2b540,0xb43eae78,0xbbb7bbf6,
0x395d3a47,0xb9f0b8f6,0xb889b6c1,0xba97bb41,0x363c384d,0xbb5ebabf,0xba73b992,0xb8bcb9be,0x3be13c00,0xb1850000,0x217f31db,0xbc00bbdd,
0x3af13b86,0xb7f3b570,0xb546b12e,0xbb8ebbe5,0x392e3a27,0xba19b91d,0xb90cb7cd,0xba35bafc,0x3599380d,0xbb7fbae6,0xbadbba0b,0xb820b93e,
0x3bdf3c00,0xb1b60000,0xa9b1304e,0xbbfebbed,0x3ade3b7d,0xb81ab59f,0xb648b31b,0xbb5cbbcd,0x38fd3a07,0xba41b943,0xb986b867,0xb9c9baae,
0x34f33796,0xbb9cbb0b,0xbb35ba78,0xb6f4b8b5,0x3bdd3c00,0xb1e80000,0xae5f2d7e,0xbbf6bbf8,0x3acb3b74,0xb83ab5ce,0xb742b481,0xbb21bbad,
0x38cc39e5,0xba67b969,0xb9f8b8e2,0xb954ba56,0x344b3710,0xbbb5bb2e,0xbb7fbad9,0xb599b822,0x3bda3c00,0xb2190000,0xb0f028b6,0xbbe7bbff,
0x3ab63b6b,0xb85ab5fd,0xb81ab570,0xbadebb86,0x389939c3,0xba8cb98d,0xba60b956,0xb8d6b9f6,0x33403687,0xbbcbbb4e,0xbbb8bb2e,0xb432b710,
0x3bff3bff,0xa6ada648,0x3bfe3bff,0xa8e8a8b6,0x3bff3bff,0xa776a711,0x3bfe3bfe,0xa94da91b,0x3bff3bff,0xa81fa7da,0x3bfe3bfe,0xa9b1a97f,
0x3bff3bff,0xa884a852,0x3bfe3bfe,0xaa16a9e3,0x3bef3bf1,0xb029afd6,0x3bda3bdd,0xb219b1db,0x3bea3bed,0xb0a6b067,0x3bd43bd7,0xb294b257,
0x3be53be8,0xb122b0e4,0x3bce3bd1,0xb30fb2d2,0x3be03be3,0xb19eb160,0x3bc63bca,0xb389b34c,0x3bc83bce,0xb371b303,0x3b873b91,0xb56ab534,
0x3bba3bc1,0xb426b3df,0x3b733b7d,0xb5d4b59f,0x3bab3bb2,0xb493b45d,0x3b5e3b69,0xb63cb608,0x3b9a3ba2,0xb4ffb4c9,0x3b473b53,0xb6a4b670,
0x3b8b3b99,0xb552b505,0x3b073b1a,0xb7a6b75e,0x3b6f3b7d,0xb5ebb59f,0x3ade3af3,0xb81ab7ee,0x3b4f3b5f,0xb682b637,0x3ab33ac9,0xb85fb83d,
0x3b2c3b3e,0xb715b6cc,0x3a853a9c,0xb8a3b881,0x3b3a3b50,0xb6ddb67c,0x3a5c3a7c,0xb8dbb8b0,0x3b0a3b22,0xb79bb73d,0x3a193a3b,0xb92eb905,
0x3ad53af0,0xb82ab7f9,0x39d239f6,0xb97db956,0x3a9b3ab8,0xb884b858,0x398639ad,0xb9c9b9a4,0x3ad53af6,0xb82ab7e3,0x398b39ba,0xb9c5b996,
0x3a8c3ab1,0xb899b862,0x3929395b,0xba1db9f2,0x3a3d3a65,0xb902b8ce,0x38c138f6,0xba6fba47,0x39e73a13,0xb966b935,0x3855388c,0xbababa95,
0x3a5c3a8a,0xb8dbb89b,0x389938d8,0xba8cba5e,0x39f83a2b,0xb954b918,0x38153858,0xbae1bab8,0x398b39c3,0xb9c5b98d,0x371537a1,0xbb2cbb08,
0x39163951,0xba2db9fa,0x35f73687,0xbb6cbb4e,0x39d23a0f,0xb97db93a,0x371537b7,0xbb2cbb02,0x394f3992,0xb9fcb9be,0x35c83670,0xbb76bb53,
0x38c13909,0xba6fba37,0x346f351d,0xbbb0bb95,0x382a3877,0xbad5baa3,0x3219337d,0xbbdabbc7,0x39373984,0xba11b9cb,0x34cf3593,0xbba1bb80,
0x389438e7,0xba90ba52,0x327c3408,0xbbd6bbbe,0x37c8383d,0xbafebac9,0x2e9130e4,0xbbf5bbe8,0x36543710,0xbb59bb2e,0x16482aac,0xbc00bbfd,
0x388e38ec,0xba93ba4f,0x30d732a1,0xbbe8bbd4,0x3790382d,0xbb0dbad3,0x28e82e14,0xbbfebbf7,0x35eb36c1,0xbb6fbb41,0xaccea4b6,0xbbfabc00,
0x34323511,0xbbb8bb97,0xb201b036,0xbbdcbbee,0x37b23848,0xbb04bac2,0x96482bd9,0xbc00bbfc,0x35df36cc,0xbb71bb3e,0xb010ac1f,0xbbefbbfc,
0x33eb34ed,0xbbc0bb9d,0xb402b20d,0xbbbfbbdb,0x2fef31f4,0xbbf0bbdc,0xb5ebb4f9,0xbb6fbb9b,0x36313732,0xbb60bb25,0xb0f0ad7e,0xbbe7bbf8,
0x341a3529,0xbbbcbb93,0xb49fb31b,0xbba9bbcd,0x2fbd320d,0xbbf1bbdb,0xb6afb5ab,0xbb45bb7b,0xa4522aac,0xbc00bbfd,0xb850b7ac,0xbabdbb05,
0x349f35c2,0xbba9bb77,0xb4dbb365,0xbb9fbbc9,0x308d32ea,0xbbebbbd0,0xb715b5fd,0xbb2cbb6b,0x9fdb2c51,0xbc00bbfb,0xb894b812,0xba90bae3,
0xb109ad4c,0xbbe6bbf9,0xb982b90e,0xb9cdba33,0x32013444,0xbbdcbbb6,0xb721b5f1,0xbb2abb6e,0x26ad2edc,0xbbffbbf4,0xb8adb822,0xba7ebad9,
0xb05bab11,0xbbedbbfd,0xb9aab930,0xb9a6ba17,0xb4b7b2ea,0xbba5bbd0,0xba81ba1b,0xb8a8b92b,0x2d653179,0xbbf9bbe2,0xb89eb807,0xba89bae9,
0xadc99a48,0xbbf8bc00,0xb9afb92b,0xb9a1ba1b,0xb432b1aa,0xbbb8bbe0,0xba93ba27,0xb88eb91d,0xb6d2b587,0xbb3dbb82,0xbb45baf3,0xb6afb7ee,
0xa51b2cb5,0xbc00bbfa,0xb990b900,0xb9c0ba3f,0xb294af40,0xbbd4bbf3,0xba89ba13,0xb89eb935,0xb625b4bd,0xbb63bba4,0xbb47baf0,0xb6a4b7f9,
0xb865b780,0xbab0bb11,0xbbc5bb8f,0xb3a2b540,0xafefa648,0xbbf0bbff,0xba60b9dc,0xb8d6b972,0xb517b31b,0xbb96bbcd,0xbb35bad3,0xb6f4b82d,
0xb7feb693,0xbaeebb4b,0xbbc0bb84,0xb3ebb57c,0xb94ab8ab,0xba00ba7f,0xbbfdbbe9,0xaa7ab0cb,0xb340afd6,0xbbcbbbf1,0xbb0aba99,0xb79bb887,
0xb6d2b540,0xbb3dbb8f,0xbbaebb67,0xb47bb614,0xb8dbb828,0xba5cbad6,0xbbfbbbe0,0xac9cb1aa,0xba15b980,0xb933b9d0,0xbbecbbff,0x30742852,
0xb53ab303,0xbb90bbce,0xbb89bb30,0xb55eb705,0xb83ab6e3,0xbacbbb39,0xbbf2bbca,0xaf8bb34c,0xb9a1b8f6,0xb9afba47,0xbbf5bc00,0x2ec39e48,
0xbac1ba3b,0xb84ab905,0xbb92bbd0,0x352f32ea,0xb6c6b505,0xbb3fbb99,0xbbdcbba0,0xb201b4d5,0xb8fdb838,0xba41bacc,0xbbfebbfb,0x2a16ac83,
0xba50b9b1,0xb8eab99f,0xbbaebbe4,0x347b3147,0xbb4abad9,0xb699b822,0xbaf1bb5d,0x37f33642,0xb820b67c,0xbadbbb50,0xbbffbbe6,0xa884b115,
0xb9afb8f1,0xb9a1ba4b,0xbbd2bbf8,0x32c62db0,0xbae5ba56,0xb80fb8e2,0xbb2abb8c,0x3721354c,0xbbaebb58,0xb47bb659,0xba11baaa,0x3937386d,
0xb8d1b7e3,0xba64baf6,0xbbf2bc00,0x2f8ba248,0xba4db99b,0xb8eeb9b5,0xbb6fbbc1,0x35eb33df,0xbb5cbae3,0xb648b812,0xba6bbafc,0x38c737cd,
0xbbebbbb4,0xb08db451,0xb8f8b9be,0x3a453992,0xb974b89b,0xb9daba8a,0xbbb5bbed,0x344b304e,0xbad5ba33,0xb82ab90e,0xbad8bb58,0x38253659,
0xbbb3bb55,0xb457b665,0xb979ba37,0x39d63909,0xbc00bbed,0x9648b067,0xb764b8a0,0x3b183a87,0xba09b93a,0xb941ba0f,0xbb4abbaf,0x36993475,
0xbb45bab8,0xb6afb858,0xba11babf,0x3937384d,0xbbeabbab,0xb0a6b48d,0xb85ab943,0x3ab63a07,0xbbecbc00,0x30749a48,0xb493b6b5,0x3bab3b43,
0xba8cb9cb,0xb899b984,0xbab3bb46,0x385f36aa,0xbb9cbb28,0xb4f3b726,0xb91fb9fa,0x3a253951,0xbc00bbe4,0xa452b147,0xb631b828,0x3b603ad6,
0xbbb0bbee,0x346f3036,0xae5fb3df,0x3bf63bc1,0xbafeba4f,0xb7c8b8ec,0xb9f4bab5,0x3958385d,0xbbd8bb82,0xb24bb587,0xb80ab90e,0x3ae83a33,
0xbbf3bbfe,0x2f27a97f,0xb2f7b5da,0x3bcf3b72,0xbb4cbbb7,0x368d3438,0x2dc9ac1f,0x3bf83bfc,0xbb5cbac2,0xb648b848,0xb911b9fe,0x3a31394d,
0xbbf9bbc4,0xad33b3ae,0xb5b1b802,0x3b7a3aed,0xbbc5bbf9,0x33a22d1a,0xa94db26f,0x3bfe3bd6,0xbac4bb5d,0x38453642,0x346f2fa4,0x3bb03bf1,
0xbba5bb25,0xb4b7b732,0xb80fb927,0x3ae53a1f,0xbbffbbee,0x2884b036,0xb24bb5b6,0x3bd83b79,0xbb76bbd6,0x35c8326f,0x305ba7da,0x3bed3bff,
0xba19bae0,0x392e3817,0x374234c9,0x3b213ba2,0xbbd9bb77,0xb232b5c2,0xb5ebb832,0x3b6f3ad0,0xbbe8bc00,0x30d7a57f,0xa81fb288,0x3bff3bd5,
0xbb07bb95,0x37a6351d,0x34f33080,0x3b9c3bec,0xb94fba43,0x39fc38fb,0x38ea3780,0x3a503b11,0xbbf8bbb6,0xadc9b444,0xb328b64e,0x3bcc3b5a,
0xbbb7bbf8,0x343e2db0,0x3042a9e3,0x3bee3bfe,0xba7abb36,0x38b236ee,0x379034ed,0x3b0d3b9d,0xb86ab989,0x3aac39c7,0x3a0438fb,0x39463a43,
0xbc00bbe2,0x2311b179,0xac9cb414,0x3bfb3bbc,0xbb6abbd7,0x36023257,0x34b72f40,0x3ba53bf3,0xb9d2babc,0x397d3852,0x38f83775,0x3a453b14,
0xb6ddb8b5,0x3b3a3a78,0x3ae83a0b,0x380a393e,0xbbf2bbfa,0x2f8bacb5,0x2d33af0e,0x3bf93bf4,0xbb04bb9e,0x37b234e1,0x372c3451,0x3b273bb4,
0xb911ba27,0x3a31391d,0x3a0038e2,0x394a3a56,0xb4c3b796,0x3ba33b0b,0x3b8b3ae6,0x3552380d,0x4c004c00,0x26480000,0x4c004c00,0x33113248,
0x4c004c00,0x2cb62a48,0x4c004c00,0x345233db,0x4c004c00,0x2fdb2e48,0x4c004c00,0x351b34b6,0x4c004c00,0x317f30b6,0x4bff4c00,0x35e4357f,
0x4c004c00,0x2fdb0000,0x4bfb4bfc,0x3c6a3bd9,0x4bff4c00,0x35e433db,0x4bf94bfa,0x3d653ce7,0x4bfe4bff,0x38e837da,0x4bf64bf7,0x3e5f3de2,
0x4bfd4bfe,0x3ade39e3,0x4bf24bf4,0x3f593edc,0x4c004c00,0x33110000,0x4bf04bf4,0x3fef3f0e,0x4bfe4bff,0x394d3711,0x4be84bed,0x40d74067,
0x4bfb4bfd,0x3c6a3b11,0x4bdf4be4,0x41b64147,0x4bf64bf9,0x3e2d3d4c,0x4bd44bda,0x42944226,0x4c004c00,0x351b0000,0x4bdf4be6,0x41b64115,
0x4bfc4bfe,0x3ba7391b,0x4bcf4bd7,0x42f74257,0x4bf64bf9,0x3e5f3d1a,0x4bbc4bc6,0x441a4396,0x4bec4bf1,0x40743fa4,0x4ba54bb1,0x44b74469,
0x4bff4c00,0x36ad0000,0x4bc84bd4,0x437142a1,0x4bfa4bfd,0x3d003aac,0x4bac4bbb,0x44874420,0x4bef4bf5,0x40293eaa,0x4b8b4b9d,0x455244ed,
0x4bde4be7,0x41cf40fd,0x4b654b79,0x461a45b6,0x4bff4c00,0x381f0000,0x4bab4bbc,0x44934414,0x4bf64bfc,0x3e2d3c1f,0x4b814b97,0x458d4511,
0x4be54bef,0x4122401d,0x4b4f4b69,0x46824608,0x4bcc4bda,0x43284226,0x4b164b33,0x476f46f9,0x4bfe4c00,0x38e80000,0x4b874ba0,0x456a44d5,
0x4bf24bfa,0x3f593ce7,0x4b4c4b6b,0x468d45fd,0x4bda4be8,0x421940e4,0x4b074b2b,0x47a6471b,0x4bb74bca,0x443e434c,0x4ab64ae0,0x485a4817,
0x4bfe4c00,0x39b10000,0x4b5e4b80,0x463c4593,0x4bee4bf8,0x40423db0,0x4b104b39,0x478546e3,0x4bce4be0,0x430f41aa,0x4ab34ae3,0x485f4812,
0x4b9e4bb7,0x44e74438,0x4a494a7f,0x48f348ab,0x4bfd4c00,0x3a7a0000,0x4b2f4b5a,0x470a464e,0x4be84bf6,0x40d73e78,0x4acb4aff,0x483a47c2,
0x4bbf4bd6,0x4402426f,0x4a544a92,0x48e54891,0x4b814ba2,0x458d44c9,0x49cd4a13,0x49824935,0x4bfd4c00,0x3b430000,0x4afb4b30,0x47d24705,
0x4be24bf3,0x416c3f40,0x4a7e4abf,0x48ad484d,0x4bae4bcb,0x447b4334,0x49eb4a37,0x49624909,0x4b604b8a,0x46314558,0x4946499b,0x4a0449b5,
0x4bfc4c00,0x3c060000,0x4ac14b02,0x484a47b7,0x4bdc4bf0,0x42014004,0x4a294a78,0x491b48b5,0x4b9c4bc0,0x44f343f7,0x497949d4,0x49d6497b,
0x4b3d4b70,0x46d245e5,0x48b24918,0x4a7a4a2b,0x4bfb4c00,0x3c6a0000,0x4a814ad0,0x48a84832,0x4bd44bed,0x42944067,0x49cd4a2b,0x49824918,
0x4b874bb2,0x456a445d,0x48fd4969,0x4a4149e5,0x4b164b53,0x476f4670,0x4815488c,0x4ae14a95,0x4bfa4c00,0x3cce0000,0x4a3d4a99,0x49024887,
0x4bcc4be9,0x432840cb,0x496b49d8,0x49e34976,0x4b714ba4,0x45df44bd,0x487a48f6,0x4aa24a47,0x4aeb4b33,0x480546f9,0x46dd47ee,0x4b3a4af3,
0x4bf94c00,0x3d330000,0x49f44a5e,0x495848d8,0x4bc34be5,0x43ba412e,0x49024980,0x4a3d49d0,0x4b594b95,0x4654451d,0x47dd487c,0x4af74aa0,
0x4abd4b11,0x48504780,0x458146b5,0x4b834b43,0x4bf84c00,0x3d970000,0x49a64a1f,0x49aa4927,0x4bba4be1,0x44264191,0x48944922,0x4a904a23,
0x4b3f4b84,0x46c6457c,0x46bb47f9,0x4b424af0,0x4a8c4aed,0x48994802,0x441a4570,0x4bbc4b86,0x4bf74c00,0x3dfb0000,0x495449dc,0x49f84972,
0x4bb04bdc,0x446f41f4,0x482048bf,0x4adb4a71,0x4b244b72,0x473745da,0x458d46ee,0x4b814b36,0x4a584ac6,0x48e04842,0x41534420,0x4be34bbb,
0x4bf64c00,0x3e5f0000,0x48fd4996,0x4a4149ba,0x4ba54bd7,0x44b74257,0x474e4858,0x4b1e4ab8,0x4b074b5f,0x47a64637,0x445745da,0x4bb34b72,
0x4a214a9c,0x49244881,0x3cce4191,0x4bfa4be1,0x4bf54c00,0x3ec30000,0x48a3494d,0x4a8549fe,0x4b9a4bd2,0x44ff42b9,0x465447d8,0x4b594af9,
0x4ae84b4b,0x480a4693,0x423244bd,0x4bd94ba4,0x49e74a71,0x496648bf,0xb4523db0,0x4c004bf8,0x4bf34c00,0x3f270000,0x48454900,0x4ac44a3f,
0x4b8e4bcd,0x4546431b,0x455246f9,0x4b8b4b33,0x4ac74b36,0x484046ee,0x3f594334,0x4bf24bcb,0x49aa4a43,0x49a648fb,0xbef52a48,0x4bf44c00,
0x4bf24c00,0x3f8b0000,0x47c848b0,0x4afe4a7c,0x4b814bc7,0x458d437d,0x444b4614,0x4bb54b67,0x4aa54b20,0x48744748,0x388440e4,0x4bff4be8,
0x496b4a13,0x49e34935,0xc263bd4c,0x4bd74bf9,0x4bf04c00,0x3fef0000,0x46ff485d,0x4b324ab5,0x4b734bc1,0x45d443df,0x427c4529,0x4bd64b93,
0x4a814b08,0x48a847a1,0xb9b13d1a,0x4bfe4bf9,0x492949e1,0x4a1d496d,0xc49fc160,0x4ba94be3,0x4bef4c00,0x40290000,0x46314807,0x4b604ae9,
0x4b654bbb,0x461a4420,0x405b4438,0x4bed4bb7,0x4a5c4af0,0x48db47f9,0xbfef2e48,0x4bf04c00,0x48e549ad,0x4a5449a4,0xc602c408,0x4b6a4bbe,
0x4bed4c00,0x405b0000,0x455e475e,0x4b894b1a,0x4b574bb4,0x465f4451,0x3c6a4288,0x4bfb4bd5,0x4a354ad6,0x490c4828,0xc27cbc51,0x4bd64bfb,
0x489e4976,0x4a8949d8,0xc759c558,0x4b1b4b8a,0x4beb4c00,0x408d0000,0x448746aa,0x4bac4b46,0x4b474bad,0x46a44481,0x26484099,0x4c004beb,
0x4a0d4abc,0x493c4852,0xc47bc080,0x4bae4bec,0x4855493e,0x4aba4a0b,0xc850c69e,0x4abd4b49,0x4be94c00,0x40be0000,0x435945f1,0x4bc94b6e,
0x4b374ba6,0x46e844b1,0xbc383d4c,0x4bfc4bf9,0x49e34aa0,0x496b487c,0xc5b1c2d2,0x4b7a4bd1,0x480a4905,0x4ae84a3b,0xc8eac7d8,0x4a504af9,
0x4be74c00,0x40f00000,0x419e4534,0x4be04b91,0x4b274b9e,0x472c44e1,0xc042357f,0x4bee4c00,0x49b84a83,0x499948a6,0xc6ddc48d,0x4b3a4bab,
0x477a48c9,0x4b134a69,0xc979c881,0x49d64a9c,0x4be54c00,0x41220000,0x3fbd4475,0x4bf14baf,0x4b164b97,0x476f4511,0xc263b91b,0x4bd74bfe,
0x498b4a65,0x49c548ce,0xc7fec5ab,0x4aee4b7b,0x46dd488c,0x4b3a4a95,0xc9fcc90e,0x494f4a33,0x4be34c00,0x41530000,0x3c384365,0x4bfc4bc9,
0x4b044b8f,0x47b24540,0xc43ebe78,0x4bb74bf6,0x495d4a47,0x49f048f6,0xc889c6c1,0x4a974b41,0x463c484d,0x4b5e4abf,0xca73c992,0x48bc49be,
0x4be14c00,0x41850000,0x317f41db,0x4c004bdd,0x4af14b86,0x47f34570,0xc546c12e,0x4b8e4be5,0x492e4a27,0x4a19491d,0xc90cc7cd,0x4a354afc,
0x4599480d,0x4b7f4ae6,0xcadbca0b,0x4820493e,0x4bdf4c00,0x41b60000,0xb9b1404e,0x4bfe4bed,0x4ade4b7d,0x481a459f,0xc648c31b,0x4b5c4bcd,
0x48fd4a07,0x4a414943,0xc986c867,0x49c94aae,0x44f34796,0x4b9c4b0b,0xcb35ca78,0x46f448b5,0x4bdd4c00,0x41e80000,0xbe5f3d7e,0x4bf64bf8,
0x4acb4b74,0x483a45ce,0xc742c481,0x4b214bad,0x48cc49e5,0x4a674969,0xc9f8c8e2,0x49544a56,0x444b4710,0x4bb54b2e,0xcb7fcad9,0x45994822,
0x4bda4c00,0x42190000,0xc0f038b6,0x4be74bff,0x4ab64b6b,0x485a45fd,0xc81ac570,0x4ade4b86,0x489949c3,0x4a8c498d,0xca60c956,0x48d649f6,
0x43404687,0x4bcb4b4e,0xcbb8cb2e,0x44324710,0x4bd84c00,0x424b0000,0xc2adb248,0x4bd34c00,0x4aa24b62,0x487a462b,0xc88ec659,0x4a934b58,
0x4865499f,0x4ab049b1,0xcabdc9c3,0x4850498d,0x41e845fd,0x4bdd4b6b,0xcbe1cb74,0x418545ce,0x4bd64c00,0x427c0000,0xc432bbd9,0x4bb84bfc,
0x4a8c4b58,0x48994659,0xc8fdc73d,0x4a414b22,0x4830497b,0x4ad149d4,0xcb10ca27,0x4785491d,0x408d4570,0x4beb4b86,0xcbf9cbad,0x3d334481,
0x4bd34c00,0x42ad0000,0xc50bbf0e,0x4b984bf4,0x4a764b4e,0x48b74687,0xc966c80d,0x49e74ae6,0x47f34956,0x4af149f6,0xcb57ca83,0x465f48a6,
0x3e5f44e1,0x4bf64b9e,0xcc00cbd7,0xb17f4257,0x4bd04c00,0x42de0000,0xc5dfc115,0x4b714be6,0x4a604b43,0x48d646b5,0xc9c9c877,0x49864aa3,
0x47854930,0x4b104a17,0xcb92cad6,0x452f4828,0x3b434451,0x4bfd4bb4,0xcbf5cbf3,0xbe913f40,0x4bce4c00,0x430f0000,0xc6afc2a1,0x4b454bd4,
0x4a494b39,0x48f346e3,0xca25c8dd,0x491f4a5a,0x47154909,0x4b2c4a37,0xcbc0cb20,0x43eb4748,0x3311437d,0x4c004bc7,0xcbd9cbff,0xc2323711,
0x4bcb4c00,0x43400000,0xc77ac414,0x4b134bbc,0x4a314b2e,0x49114710,0xca7ac93e,0x48b24a0b,0x46a448e2,0x4b474a56,0xcbe2cb5f,0x416c4637,
0xb7764257,0x4bff4bd7,0xcbaccbfd,0xc487bb75,0x4bc84c00,0x43710000,0xc820c4d5,0x4adb4ba0,0x4a194b22,0x492e473d,0xcac7c99b,0x484049b5,
0x463148ba,0x4b604a74,0xcbf8cb95,0x3dc9451d,0xbc9c412e,0x4bfb4be5,0xcb6fcbeb,0xc5ebc099,0x4bc54c00,0x43a20000,0xc87fc593,0x4a9e4b80,
0x4a004b17,0x494a476a,0xcb0dc9f2,0x4790495b,0x45bc4891,0x4b784a92,0xcc00cbc0,0x317f43f7,0xbf594004,0x4bf24bf0,0xcb21cbca,0xc742c34c,
0x4bc24c00,0x43d30000,0xc8dbc64e,0x4a5c4b5a,0x49e74b0b,0x49664796,0xcb4aca43,0x469948fb,0x45464867,0x4b8e4aae,0xcbfbcbe0,0xbc6a41aa,
0xc1093db0,0x4be64bf8,0xcac4cb9b,0xc845c4f9,0x4bbf4c00,0x44020000,0xc933c705,0x4a154b30,0x49cd4aff,0x498247c2,0xcb7fca8e,0x45994896,
0x44cf483d,0x4ba14ac9,0xcbe9cbf5,0xc0be3eaa,0xc2633aac,0x4bd74bfd,0xca58cb5d,0xc8e0c642,0x4bbc4c00,0x441a0000,0xc986c7b7,0x49c94b02,
0x49b34af3,0x499d47ee,0xcbabcad3,0x4493482d,0x44574812,0x4bb34ae3,0xcbcbcbff,0xc34037da,0xc3ba33db,0x4bc34c00,0xc9dfcb11,0xc970c780,
0x4bb84c00,0x44320000,0xc9d6c832,0x49794ad0,0x49994ae6,0x49b8480d,0xcbcecb11,0x430f4780,0x43ba47cd,0x4bc34afc,0xcb9fcbfe,0xc4dbb97f,
0xc487b57f,0x4bac4c00,0xc958cab8,0xc9f4c858,0x4bb54c00,0x444b0000,0xca21c887,0x49244a99,0x497d4ad9,0x49d24822,0xcbe7cb49,0x40f0469e,
0x42c64775,0x4bd24b14,0xcb68cbf2,0xc60ebf72,0xc52fbb75,0x4b924bfd,0xc8c7ca52,0xca6bc8e7,0x4bb24c00,0x44630000,0xca67c8d8,0x48cc4a5e,
0x49624acc,0x49eb4838,0xcbf8cb79,0x3d9745b6,0x41cf471b,0x4bde4b2b,0xcb24cbdb,0xc737c20d,0xc5d4be14,0x4b734bf7,0xc82ac9e1,0xcad5c96d,
0x4bae4c00,0x447b0000,0xcaa9c927,0x486f4a1f,0x49464abf,0x4a04484d,0xcc00cba2,0x351b44c9,0x40d746c1,0x4be84b41,0xcad5cbb9,0xc82ac42c,
0xc676c036,0x4b524bee,0xc70ac964,0xcb2fc9e9,0x4bab4c00,0x44930000,0xcae5c972,0x480f49dc,0x49294ab1,0x4a1d4862,0xcbfecbc4,0xba1643ae,
0x3fbd4665,0x4bf14b55,0xca7acb8c,0xc8b2c54c,0xc715c160,0x4b2c4be3,0xc5b1c8dd,0xcb7aca5a,0x4ba74c00,0x44ab0000,0xcb1bc9ba,0x47594996,
0x490c4aa3,0x4a354877,0xcbf2cbdf,0xbf5941c3,0x3dc94608,0x4bf84b69,0xca15cb55,0xc933c665,0xc7b2c288,0x4b044bd5,0xc44bc84d,0xcbb5cabf,
0x4ba34c00,0x44c30000,0xcb4cc9fe,0x468d494d,0x48ee4a95,0x4a4d488c,0xcbdecbf1,0xc1cf3fa4,0x3ba745ab,0x4bfc4b7b,0xc9a6cb14,0xc9aac775,
0xc825c3ae,0x4ad84bc4,0xc1b6c76a,0xcbdfcb17,0x4b9f4c00,0x44db0000,0xcb78ca3f,0x45bc4900,0x48d14a87,0x4a6448a0,0xcbc0cbfd,0xc3eb3b75,
0x3776454c,0x4bff4b8c,0xc92ecac9,0xca19c83d,0xc86fc469,0x4aa94bb1,0xbd97c62b,0xcbf8cb62,0x4b9c4c00,0x44f30000,0xcb9eca7c,0x44e748b0,
0x48b24a78,0x4a7a48b5,0xcb9acc00,0xc4ffaa48,0xa64844ed,0x4c004b9d,0xc8adca74,0xca7ec8ba,0xc8b7c4f9,0x4a764b9b,0x2cb6c4e1,0xcc00cb9e,
0x4b984c00,0x450b0000,0xcbbdcab5,0x440e485d,0x48944a69,0x4a9048c9,0xcb6acbfc,0xc602bc1f,0xb81f448d,0x4bff4bab,0xc825ca17,0xcad8c930,
0xc8fdc587,0x4a414b82,0x3e2dc31b,0xcbf6cbcd,0x4b944c00,0x45230000,0xcbd7cae9,0x42634807,0x48744a5a,0x4aa548dd,0xcb32cbf0,0xc6ffc004,
0xbc06442c,0x4bfc4bb9,0xc72cc9b1,0xcb27c99f,0xc941c614,0x4a094b67,0x4201c067,0xcbdccbed,0x4b904c00,0x453a0000,0xcbeacb1a,0x40a6475e,
0x48554a4b,0x4aba48f1,0xcaf1cbdc,0xc7f3c1f4,0xbdfb4396,0x4bf74bc6,0xc602c943,0xcb6aca07,0xc982c69e,0x49cd4b49,0x446fbaac,0xcbb0cbfd,
0x4b8b4c00,0x45520000,0xcbf8cb46,0x3dc946aa,0x48354a3b,0x4ace4905,0xcaa9cbc1,0xc86fc3df,0xbfef42d2,0x4bf04bd1,0xc4cfc8ce,0xcba1ca65,
0xc9c0c726,0x49904b28,0x45d43852,0xcb73cbff,0x4b874c00,0x456a0000,0xcbffcb6e,0x388445f1,0x48154a2b,0x4ae14918,0xca58cb9e,0xc8e0c4e1,
0xc0f0420d,0x4be74bdb,0xc328c852,0xcbcccabc,0xc9fcc7ac,0x494f4b05,0x472c3fa4,0xcb27cbf1,0x4b834c00,0x45810000,0xcc00cb91,0xb51b4534,
0x47e84a1b,0x4af4492b,0xca00cb74,0xc94ac5ce,0xc1e84147,0x4bdd4be4,0xc0a6c7a1,0xcbeacb08,0xca35c817,0x490c4ae0,0x483a4288,0xcacbcbd5,
0x4b7f4c00,0x45990000,0xcbfacbaf,0xbcce4475,0x47a64a0b,0x4b07493e,0xc9a1cb43,0xc9afc6b5,0xc2de4080,0x4bd04bec,0xbc38c693,0xcbfccb4b,
0xca6bc858,0x48c74ab8,0x48d64499,0xca60cbaa,0x4b7a4c00,0x45b10000,0xcbefcbc9,0xc0294365,0x476449fa,0x4b184951,0xc93ccb0b,0xca0dc796,
0xc3d33f72,0x4bc24bf2,0x3311c57c,0xcc00cb84,0xca9ec896,0x487f4a8e,0x496645e5,0xc9e7cb70,0x4b764c00,0x45c80000,0xcbddcbdd,0xc1e841db,
0x472149e9,0x4b2a4964,0xc8d1cacc,0xca64c838,0xc4633de2,0x4bb24bf7,0x3dfbc45d,0xcbf7cbb2,0xcacec8d3,0x48354a62,0x49eb4726,0xc962cb28,
0x4b714c00,0x45df0000,0xcbc5cbed,0xc3a2404e,0x46dd49d8,0x4b3a4976,0xc85fca87,0xcab3c8a0,0xc4db3c51,0x4b9f4bfb,0x4185c26f,0xcbe1cbd6,
0xcafbc90e,0x47d24a33,0x4a64482d,0xc8d1cad3,0x4b6c4c00,0x45f70000,0xcba7cbf8,0xc4ab3d7e,0x469949c7,0x4b4a4989,0xc7d2ca3b,0xcafbc905,
0xc552397f,0x4b8b4bfe,0x4402c01d,0xcbbfcbef,0xcb24c948,0x47374a02,0x4ace48bf,0xc835ca71,0x4b684c00,0x460e0000,0xcb83cbff,0xc58138b6,
0x465449b5,0x4b59499b,0xc6ddc9e9,0xcb3ac964,0xc5c834b6,0x4b764c00,0x453abb11,0xcb90cbfd,0xcb4ac980,0x469949d0,0x4b2a4948,0xc721ca02,
0x2c002c00,0x2c002c00,0x2c002c00,0x2c002c00,0x2b642c00,0x261f29a8,0xa61f0000,0xab64a9a8,0x29a82c00,0xa9a80000,0xa9a8ac00,0x29a80000,
0x261f2c00,0xab64a9a8,0x2b640000,0xa61f29a8,0x2c00,0xac00,0x2c00,0xac00,0xa61f2c00,0x2b64a9a8,0xab640000,0x261f29a8,
0xa9a82c00,0x29a80000,0x29a8ac00,0xa9a80000,0xab642c00,0xa61f29a8,0x261f0000,0x2b64a9a8,0,0,0,0,
0x261f0000,0x2b6429a8,0x2b642c00,0x261f29a8,0x29a80000,0x29a82c00,0xa9a80000,0xa9a8ac00,0x2b640000,0xa61f29a8,0xa61fac00,0x2b6429a8,
0x2c000000,0xac000000,0x2c000000,0xac000000,0x2b640000,0xa61fa9a8,0xa61f2c00,0x2b64a9a8,0x29a80000,0x29a8ac00,0xa9a80000,0xa9a82c00,
0x261f0000,0x2b64a9a8,0x2b64ac00,0x261fa9a8,0xac002c00,0xac002c00,0xac002c00,0xac002c00,0xab642c00,0xa61f29a8,0x261f0000,0x2b64a9a8,
0xa9a82c00,0x29a80000,0x29a8ac00,0xa9a80000,0xa61f2c00,0x2b64a9a8,0xab640000,0x261f29a8,0x2c00,0xac00,0x2c00,0xac00,
0x261f2c00,0xab64a9a8,0x2b640000,0xa61f29a8,0x29a82c00,0xa9a80000,0xa9a8ac00,0x29a80000,0x2b642c00,0x261f29a8,0xa61f0000,0xab64a9a8,
0,0,0,0,0xa61f0000,0xab6429a8,0xab642c00,0xa61f29a8,0xa9a80000,0xa9a82c00,0x29a80000,0x29a8ac00,
0xab640000,0x261f29a8,0x261fac00,0xab6429a8,0xac000000,0x2c000000,0xac000000,0x2c000000,0xab640000,0x261fa9a8,0x261f2c00,0xab64a9a8,
0xa9a80000,0xa9a8ac00,0x29a80000,0x29a82c00,0xa61f0000,0xab64a9a8,0xab64ac00,0xa61fa9a8,0,0,0,0,
0xa61f0000,0xab64a9a8,0xab64ac00,0xa61fa9a8,0xa9a80000,0xa9a8ac00,0x29a80000,0x29a82c00,0xab640000,0x261fa9a8,0x261f2c00,0xab64a9a8,
0xac000000,0x2c000000,0xac000000,0x2c000000,0xab640000,0x261f29a8,0x261fac00,0xab6429a8,0xa9a80000,0xa9a82c00,0x29a80000,0x29a8ac00,
0xa61f0000,0xab6429a8,0xab642c00,0xa61f29a8,0x2c002c00,0x2c002c00,0x2c002c00,0x2c002c00,0x2b642c00,0x261f29a8,0xa61f0000,0xab64a9a8,
0x29a82c00,0xa9a80000,0xa9a8ac00,0x29a80000,0x261f2c00,0xab64a9a8,0x2b640000,0xa61f29a8,0x2c00,0xac00,0x2c00,0xac00,
0xa61f2c00,0x2b64a9a8,0xab640000,0x261f29a8,0xa9a82c00,0x29a80000,0x29a8ac00,0xa9a80000,0xab642c00,0xa61f29a8,0x261f0000,0x2b64a9a8,
0,0,0,0,0x261f0000,0x2b64a9a8,0x2b64ac00,0x261fa9a8,0x29a80000,0x29a8ac00,0xa9a80000,0xa9a82c00,
0x2b640000,0xa61fa9a8,0xa61f2c00,0x2b64a9a8,0x2c000000,0xac000000,0x2c000000,0xac000000,0x2b640000,0xa61f29a8,0xa61fac00,0x2b6429a8,
0x29a80000,0x29a82c00,0xa9a80000,0xa9a8ac00,0x261f0000,0x2b6429a8,0x2b642c00,0x261f29a8,0xac002c00,0xac002c00,0xac002c00,0xac002c00,
0xab642c00,0xa61f29a8,0x261f0000,0x2b64a9a8,0xa9a82c00,0x29a80000,0x29a8ac00,0xa9a80000,0xa61f2c00,0x2b64a9a8,0xab640000,0x261f29a8,
0x2c00,0xac00,0x2c00,0xac00,0x261f2c00,0xab64a9a8,0x2b640000,0xa61f29a8,0x29a82c00,0xa9a80000,0xa9a8ac00,0x29a80000,
0x2b642c00,0x261f29a8,0xa61f0000,0xab64a9a8,0x2c002c00,0x2c002c00,0x2c002c00,0x2c002c00,0xab64ac00,0xa61fa9a8,0x261f0000,0x2b6429a8,
0x29a82c00,0xa9a80000,0xa9a8ac00,0x29a80000,0xa61fac00,0x2b6429a8,0xab640000,0x261fa9a8,0x2c00,0xac00,0x2c00,0xac00,
0x261fac00,0xab6429a8,0x2b640000,0xa61fa9a8,0xa9a82c00,0x29a80000,0x29a8ac00,0xa9a80000,0x2b64ac00,0x261fa9a8,0xa61f0000,0xab6429a8,
0,0,0,0,0xa61f0000,0xab64a9a8,0xab64ac00,0xa61fa9a8,0x29a80000,0x29a82c00,0xa9a80000,0xa9a8ac00,
0xab640000,0x261fa9a8,0x261f2c00,0xab64a9a8,0x2c000000,0xac000000,0x2c000000,0xac000000,0xab640000,0x261f29a8,0x261fac00,0xab6429a8,
0x29a80000,0x29a8ac00,0xa9a80000,0xa9a82c00,0xa61f0000,0xab6429a8,0xab642c00,0xa61f29a8,0xac002c00,0xac002c00,0xac002c00,0xac002c00,
0x2b64ac00,0x261fa9a8,0xa61f0000,0xab6429a8,0xa9a82c00,0x29a80000,0x29a8ac00,0xa9a80000,0x261fac00,0xab6429a8,0x2b640000,0xa61fa9a8,
0x2c00,0xac00,0x2c00,0xac00,0xa61fac00,0x2b6429a8,0xab640000,0x261fa9a8,0x29a82c00,0xa9a80000,0xa9a8ac00,0x29a80000,
0xab64ac00,0xa61fa9a8,0x261f0000,0x2b6429a8,0,0,0,0,0x261f0000,0x2b64a9a8,0x2b64ac00,0x261fa9a8,
0xa9a80000,0xa9a82c00,0x29a80000,0x29a8ac00,0x2b640000,0xa61fa9a8,0xa61f2c00,0x2b64a9a8,0xac000000,0x2c000000,0xac000000,0x2c000000,
0x2b640000,0xa61f29a8,0xa61fac00,0x2b6429a8,0xa9a80000,0xa9a8ac00,0x29a80000,0x29a82c00,0x261f0000,0x2b6429a8,0x2b642c00,0x261f29a8,
0,0,0,0,0x261f0000,0x2b6429a8,0x2b642c00,0x261f29a8,0xa9a80000,0xa9a8ac00,0x29a80000,0x29a82c00,
0x2b640000,0xa61f29a8,0xa61fac00,0x2b6429a8,0xac000000,0x2c000000,0xac000000,0x2c000000,0x2b640000,0xa61fa9a8,0xa61f2c00,0x2b64a9a8,
0xa9a80000,0xa9a82c00,0x29a80000,0x29a8ac00,0x261f0000,0x2b64a9a8,0x2b64ac00,0x261fa9a8,0x2c002c00,0x2c002c00,0x2c002c00,0x2c002c00,
0xab64ac00,0xa61fa9a8,0x261f0000,0x2b6429a8,0x29a82c00,0xa9a80000,0xa9a8ac00,0x29a80000,0xa61fac00,0x2b6429a8,0xab640000,0x261fa9a8,
0x2c00,0xac00,0x2c00,0xac00,0x261fac00,0xab6429a8,0x2b640000,0xa61fa9a8,0xa9a82c00,0x29a80000,0x29a8ac00,0xa9a80000,
0x2b64ac00,0x261fa9a8,0xa61f0000,0xab6429a8,0,0,0,0,0xa61f0000,0xab6429a8,0xab642c00,0xa61f29a8,
0x29a80000,0x29a8ac00,0xa9a80000,0xa9a82c00,0xab640000,0x261f29a8,0x261fac00,0xab6429a8,0x2c000000,0xac000000,0x2c000000,0xac000000,
0xab640000,0x261fa9a8,0x261f2c00,0xab64a9a8,0x29a80000,0x29a82c00,0xa9a80000,0xa9a8ac00,0xa61f0000,0xab64a9a8,0xab64ac00,0xa61fa9a8,
0xac002c00,0xac002c00,0xac002c00,0xac002c00,0x2b64ac00,0x261fa9a8,0xa61f0000,0xab6429a8,0xa9a82c00,0x29a80000,0x29a8ac00,0xa9a80000,
0x261fac00,0xab6429a8,0x2b640000,0xa61fa9a8,0x2c00,0xac00,0x2c00,0xac00,0xa61fac00,0x2b6429a8,0xab640000,0x261fa9a8,
0x29a82c00,0xa9a80000,0xa9a8ac00,0x29a80000,0xab64ac00,0xa61fa9a8,0x261f0000,0x2b6429a8,0x2bd92c00,0x2aa72b64,0x287229a8,0x223e261f,
0x2aa72c00,0xa23e261f,0xabd9a9a8,0xa872ab64,0x28722c00,0xabd9a61f,0x223ea9a8,0x2aa72b64,0x223e2c00,0xa872ab64,0x2aa729a8,0xabd9a61f,
0xa23e2c00,0x2872ab64,0xaaa729a8,0x2bd9a61f,0xa8722c00,0x2bd9a61f,0xa23ea9a8,0xaaa72b64,0xaaa72c00,0x223e261f,0x2bd9a9a8,0x2872ab64,
0xabd92c00,0xaaa72b64,0xa87229a8,0xa23e261f,0x223e0000,0x2872261f,0x2aa729a8,0x2bd92b64,0x28720000,0x2bd92b64,0x223e29a8,0xaaa7a61f,
0x2aa70000,0x223e2b64,0xabd9a9a8,0x2872a61f,0x2bd90000,0xaaa7261f,0x2872a9a8,0xa23e2b64,0x2bd90000,0xaaa7a61f,0x287229a8,0xa23eab64,
0x2aa70000,0x223eab64,0xabd929a8,0x2872261f,0x28720000,0x2bd9ab64,0x223ea9a8,0xaaa7261f,0x223e0000,0x2872a61f,0x2aa7a9a8,0x2bd9ab64,
0xabd92c00,0xaaa72b64,0xa87229a8,0xa23e261f,0xaaa72c00,0x223e261f,0x2bd9a9a8,0x2872ab64,0xa8722c00,0x2bd9a61f,0xa23ea9a8,0xaaa72b64,
0xa23e2c00,0x2872ab64,0xaaa729a8,0x2bd9a61f,0x223e2c00,0xa872ab64,0x2aa729a8,0xabd9a61f,0x28722c00,0xabd9a61f,0x223ea9a8,0x2aa72b64,
0x2aa72c00,0xa23e261f,0xabd9a9a8,0xa872ab64,0x2bd92c00,0x2aa72b64,0x287229a8,0x223e261f,0xa23e0000,0xa872261f,0xaaa729a8,0xabd92b64,
0xa8720000,0xabd92b64,0xa23e29a8,0x2aa7a61f,0xaaa70000,0xa23e2b64,0x2bd9a9a8,0xa872a61f,0xabd90000,0x2aa7261f,0xa872a9a8,0x223e2b64,
0xabd90000,0x2aa7a61f,0xa87229a8,0x223eab64,0xaaa70000,0xa23eab64,0x2bd929a8,0xa872261f,0xa8720000,0xabd9ab64,0xa23ea9a8,0x2aa7261f,
0xa23e0000,0xa872a61f,0xaaa7a9a8,0xabd9ab64,0xa23e0000,0xa872a61f,0xaaa7a9a8,0xabd9ab64,0xa8720000,0xabd9ab64,0xa23ea9a8,0x2aa7261f,
0xaaa70000,0xa23eab64,0x2bd929a8,0xa872261f,0xabd90000,0x2aa7a61f,0xa87229a8,0x223eab64,0xabd90000,0x2aa7261f,0xa872a9a8,0x223e2b64,
0xaaa70000,0xa23e2b64,0x2bd9a9a8,0xa872a61f,0xa8720000,0xabd92b64,0xa23e29a8,0x2aa7a61f,0xa23e0000,0xa872261f,0xaaa729a8,0xabd92b64,
0x2bd92c00,0x2aa72b64,0x287229a8,0x223e261f,0x2aa72c00,0xa23e261f,0xabd9a9a8,0xa872ab64,0x28722c00,0xabd9a61f,0x223ea9a8,0x2aa72b64,
0x223e2c00,0xa872ab64,0x2aa729a8,0xabd9a61f,0xa23e2c00,0x2872ab64,0xaaa729a8,0x2bd9a61f,0xa8722c00,0x2bd9a61f,0xa23ea9a8,0xaaa72b64,
0xaaa72c00,0x223e261f,0x2bd9a9a8,0x2872ab64,0xabd92c00,0xaaa72b64,0xa87229a8,0xa23e261f,0x223e0000,0x2872a61f,0x2aa7a9a8,0x2bd9ab64,
0x28720000,0x2bd9ab64,0x223ea9a8,0xaaa7261f,0x2aa70000,0x223eab64,0xabd929a8,0x2872261f,0x2bd90000,0xaaa7a61f,0x287229a8,0xa23eab64,
0x2bd90000,0xaaa7261f,0x2872a9a8,0xa23e2b64,0x2aa70000,0x223e2b64,0xabd9a9a8,0x2872a61f,0x28720000,0x2bd92b64,0x223e29a8,0xaaa7a61f,
0x223e0000,0x2872261f,0x2aa729a8,0x2bd92b64,0xabd92c00,0xaaa72b64,0xa87229a8,0xa23e261f,0xaaa72c00,0x223e261f,0x2bd9a9a8,0x2872ab64,
0xa8722c00,0x2bd9a61f,0xa23ea9a8,0xaaa72b64,0xa23e2c00,0x2872ab64,0xaaa729a8,0x2bd9a61f,0x223e2c00,0xa872ab64,0x2aa729a8,0xabd9a61f,
0x28722c00,0xabd9a61f,0x223ea9a8,0x2aa72b64,0x2aa72c00,0xa23e261f,0xabd9a9a8,0xa872ab64,0x2bd92c00,0x2aa72b64,0x287229a8,0x223e261f,
0xa23e0000,0xa872a61f,0xaaa7a9a8,0xabd9ab64,0x28720000,0x2bd92b64,0x223e29a8,0xaaa7a61f,0xaaa70000,0xa23eab64,0x2bd929a8,0xa872261f,
0x2bd90000,0xaaa7261f,0x2872a9a8,0xa23e2b64,0xabd90000,0x2aa7261f,0xa872a9a8,0x223e2b64,0x2aa70000,0x223eab64,0xabd929a8,0x2872261f,
0xa8720000,0xabd92b64,0xa23e29a8,0x2aa7a61f,0x223e0000,0x2872a61f,0x2aa7a9a8,0x2bd9ab64,0x2bd92c00,0x2aa72b64,0x287229a8,0x223e261f,
0xaaa7ac00,0x223ea61f,0x2bd929a8,0x28722b64,0x28722c00,0xabd9a61f,0x223ea9a8,0x2aa72b64,0xa23eac00,0x28722b64,0xaaa7a9a8,0x2bd9261f,
0xa23e2c00,0x2872ab64,0xaaa729a8,0x2bd9a61f,0x2872ac00,0xabd9261f,0x223e29a8,0x2aa7ab64,0xaaa72c00,0x223e261f,0x2bd9a9a8,0x2872ab64,
0x2bd9ac00,0x2aa7ab64,0x2872a9a8,0x223ea61f,0x223e0000,0x2872a61f,0x2aa7a9a8,0x2bd9ab64,0xa8720000,0xabd92b64,0xa23e29a8,0x2aa7a61f,
0x2aa70000,0x223eab64,0xabd929a8,0x2872261f,0xabd90000,0x2aa7261f,0xa872a9a8,0x223e2b64,0x2bd90000,0xaaa7261f,0x2872a9a8,0xa23e2b64,
0xaaa70000,0xa23eab64,0x2bd929a8,0xa872261f,0x28720000,0x2bd92b64,0x223e29a8,0xaaa7a61f,0xa23e0000,0xa872a61f,0xaaa7a9a8,0xabd9ab64,
0xabd92c00,0xaaa72b64,0xa87229a8,0xa23e261f,0x2aa7ac00,0xa23ea61f,0xabd929a8,0xa8722b64,0xa8722c00,0x2bd9a61f,0xa23ea9a8,0xaaa72b64,
0x223eac00,0xa8722b64,0x2aa7a9a8,0xabd9261f,0x223e2c00,0xa872ab64,0x2aa729a8,0xabd9a61f,0xa872ac00,0x2bd9261f,0xa23e29a8,0xaaa7ab64,
0x2aa72c00,0xa23e261f,0xabd9a9a8,0xa872ab64,0xabd9ac00,0xaaa7ab64,0xa872a9a8,0xa23ea61f,0xabd9ac00,0xaaa7ab64,0xa872a9a8,0xa23ea61f,
0x2aa72c00,0xa23e261f,0xabd9a9a8,0xa872ab64,0xa872ac00,0x2bd9261f,0xa23e29a8,0xaaa7ab64,0x223e2c00,0xa872ab64,0x2aa729a8,0xabd9a61f,
0x223eac00,0xa8722b64,0x2aa7a9a8,0xabd9261f,0xa8722c00,0x2bd9a61f,0xa23ea9a8,0xaaa72b64,0x2aa7ac00,0xa23ea61f,0xabd929a8,0xa8722b64,
0xabd92c00,0xaaa72b64,0xa87229a8,0xa23e261f,0xa23e0000,0xa872a61f,0xaaa7a9a8,0xabd9ab64,0x28720000,0x2bd92b64,0x223e29a8,0xaaa7a61f,
0xaaa70000,0xa23eab64,0x2bd929a8,0xa872261f,0x2bd90000,0xaaa7261f,0x2872a9a8,0xa23e2b64,0xabd90000,0x2aa7261f,0xa872a9a8,0x223e2b64,
0x2aa70000,0x223eab64,0xabd929a8,0x2872261f,0xa8720000,0xabd92b64,0xa23e29a8,0x2aa7a61f,0x223e0000,0x2872a61f,0x2aa7a9a8,0x2bd9ab64,
0x2bd9ac00,0x2aa7ab64,0x2872a9a8,0x223ea61f,0xaaa72c00,0x223e261f,0x2bd9a9a8,0x2872ab64,0x2872ac00,0xabd9261f,0x223e29a8,0x2aa7ab64,
0xa23e2c00,0x2872ab64,0xaaa729a8,0x2bd9a61f,0xa23eac00,0x28722b64,0xaaa7a9a8,0x2bd9261f,0x28722c00,0xabd9a61f,0x223ea9a8,0x2aa72b64,
0xaaa7ac00,0x223ea61f,0x2bd929a8,0x28722b64,0x2bd92c00,0x2aa72b64,0x287229a8,0x223e261f,0x223e0000,0x2872a61f,0x2aa7a9a8,0x2bd9ab64,
0xa8720000,0xabd92b64,0xa23e29a8,0x2aa7a61f,0x2aa70000,0x223eab64,0xabd929a8,0x2872261f,0xabd90000,0x2aa7261f,0xa872a9a8,0x223e2b64,
0x2bd90000,0xaaa7261f,0x2872a9a8,0xa23e2b64,0xaaa70000,0xa23eab64,0x2bd929a8,0xa872261f,0x28720000,0x2bd92b64,0x223e29a8,0xaaa7a61f,
0xa23e0000,0xa872a61f,0xaaa7a9a8,0xabd9ab64,0x27fe2800,0x96480000,0x273b2764,0xa2d7a21f,0x27ea27f6,0x9cb29a46,0x26dd270e,0xa41da38b,
0x27c327d9,0x9fc69e3e,0x266d26a7,0xa4c4a472,0x278827a8,0xa164a0a5,0x25ed262f,0xa55fa513,0x27c32800,0x9fc60000,0xa4c4a21f,0xa66da764,
0x25ed270e,0xa55fa38b,0xa73ba62f,0xa2d7a513,0x21642472,0xa788a6a7,0xa7fea7d9,0x16489e3e,0x9cb21a46,0xa7eaa7f6,0xa6dda7a8,0x241d20a5,
0x273b2800,0xa2d70000,0xa55fa764,0x25ed221f,0x1fc62513,0xa7c3a62f,0x1cb2a0a5,0x27ea27a8,0xa4c49e3e,0xa66da7d9,0x26dd2472,0x241d26a7,
0xa7fea70e,0x9648a38b,0x278827f6,0xa1641a46,0x266d2800,0xa4c40000,0x26dd221f,0x241d2764,0xa16420a5,0xa788a7a8,0x25ed27f6,0xa55f9a46,
0xa7fea6a7,0x1648a472,0xa2d71e3e,0xa73ba7d9,0x9fc6a62f,0x27c32513,0xa7eaa70e,0x1cb2a38b,0x255f2800,0xa5ed0000,0x21642764,0xa788a21f,
0xa66d9a46,0xa4c4a7f6,0xa7c3a38b,0x9fc6a70e,0xa41da7d9,0x26dd1e3e,0x9cb2a6a7,0x27ea2472,0x273b20a5,0x22d727a8,0x27fe2513,0x1648262f,
0x241d2800,0xa6dd0000,0xa7eaa21f,0x9cb2a764,0xa7fea38b,0x9648a70e,0x2164a513,0x2788262f,0x22d7a472,0x273b26a7,0x255f27d9,0xa5ed1e3e,
0x24c427f6,0xa66d1a46,0xa7c3a0a5,0x9fc6a7a8,0x21642800,0xa7880000,0x1648a764,0x27fe221f,0xa6dda62f,0x241da513,0x24c427a8,0xa66d20a5,
0x27ea1e3e,0x1cb227d9,0xa7c3a472,0x1fc6a6a7,0xa55f238b,0xa5eda70e,0x273b9a46,0x22d727f6,0x1cb22800,0xa7ea0000,0x27c3221f,0x9fc62764,
0xa2d7a7a8,0x273ba0a5,0xa7fe9a46,0x9648a7f6,0x255f26a7,0xa5ed2472,0x27889e3e,0x216427d9,0xa6dda513,0x241da62f,0xa66d238b,0xa4c4a70e,
0x96482800,0xa7fe0000,0xa2d72764,0xa73ba21f,0x1cb2a7f6,0x27ea1a46,0x241da70e,0x26dd238b,0x9fc627d9,0xa7c39e3e,0xa4c426a7,0xa66da472,
0x2164a7a8,0x278820a5,0x255fa62f,0x25ed2513,0x9fc62800,0xa7c30000,0xa66da21f,0x24c4a764,0x255fa70e,0x25ed238b,0x22d7262f,0xa73b2513,
0xa7882472,0xa164a6a7,0x1648a7d9,0x27fe9e3e,0x27ea9a46,0x9cb227f6,0xa41d27a8,0xa6dda0a5,0xa2d72800,0xa73b0000,0x25eda764,0x255f221f,
0x27c3a513,0x1fc6262f,0xa7ea20a5,0x1cb2a7a8,0xa66d9e3e,0x24c4a7d9,0x241d2472,0xa6dd26a7,0x1648270e,0xa7fe238b,0x2164a7f6,0x27889a46,
0xa4c42800,0xa66d0000,0x241d221f,0xa6dd2764,0x2788a0a5,0xa16427a8,0x255fa7f6,0x25ed1a46,0x1648a6a7,0x27fea472,0xa73b1e3e,0x22d7a7d9,
0xa7c3262f,0x9fc6a513,0x9cb2270e,0xa7ea238b,0xa5ed2800,0xa55f0000,0xa7882764,0xa164a21f,0x24c41a46,0xa66d27f6,0x1fc6238b,0xa7c3270e,
0x26dda7d9,0x241d1e3e,0x27eaa6a7,0x1cb22472,0xa2d7a0a5,0x273ba7a8,0x9648a513,0x27fea62f,0xa6dd2800,0xa41d0000,0x9cb2a21f,0x27eaa764,
0x1648238b,0xa7fe270e,0xa7882513,0x2164a62f,0x273ba472,0xa2d726a7,0xa5ed27d9,0xa55f1e3e,0x266da7f6,0x24c49a46,0x1fc620a5,0xa7c327a8,
0xa7882800,0xa1640000,0x27fea764,0x9648221f,0xa41d262f,0xa6dd2513,0x266da7a8,0x24c4a0a5,0x1cb21e3e,0xa7ea27d9,0x1fc6a472,0x27c3a6a7,
0x25eda38b,0xa55f270e,0xa2d71a46,0x273ba7f6,0xa7ea2800,0x9cb20000,0x9fc6221f,0xa7c32764,0xa73b27a8,0xa2d720a5,0x16481a46,0xa7fe27f6,
0xa5ed26a7,0xa55f2472,0x21649e3e,0xa78827d9,0xa41d2513,0xa6dd262f,0x24c4a38b,0xa66d270e,0xa7fe2800,0x16480000,0xa73b2764,0x22d7a21f,
0xa7ea27f6,0x1cb29a46,0xa6dd270e,0x241da38b,0xa7c327d9,0x1fc69e3e,0xa66d26a7,0x24c4a472,0xa78827a8,0x2164a0a5,0xa5ed262f,0x255fa513,
0xa7c32800,0x1fc60000,0x24c4a21f,0x266da764,0xa5ed270e,0x255fa38b,0x273ba62f,0x22d7a513,0xa1642472,0x2788a6a7,0x27fea7d9,0x96489e3e,
0x1cb21a46,0x27eaa7f6,0x26dda7a8,0xa41d20a5,0xa73b2800,0x22d70000,0x255fa764,0xa5ed221f,0x9fc62513,0x27c3a62f,0x9cb2a0a5,0xa7ea27a8,
0x24c49e3e,0x266da7d9,0xa6dd2472,0xa41d26a7,0x27fea70e,0x1648a38b,0xa78827f6,0x21641a46,0xa66d2800,0x24c40000,0xa6dd221f,0xa41d2764,
0x216420a5,0x2788a7a8,0xa5ed27f6,0x255f9a46,0x27fea6a7,0x9648a472,0x22d71e3e,0x273ba7d9,0x1fc6a62f,0xa7c32513,0x27eaa70e,0x9cb2a38b,
0xa55f2800,0x25ed0000,0xa1642764,0x2788a21f,0x266d9a46,0x24c4a7f6,0x27c3a38b,0x1fc6a70e,0x241da7d9,0xa6dd1e3e,0x1cb2a6a7,0xa7ea2472,
0xa73b20a5,0xa2d727a8,0xa7fe2513,0x9648262f,0xa41d2800,0x26dd0000,0x27eaa21f,0x1cb2a764,0x27fea38b,0x1648a70e,0xa164a513,0xa788262f,
0xa2d7a472,0xa73b26a7,0xa55f27d9,0x25ed1e3e,0xa4c427f6,0x266d1a46,0x27c3a0a5,0x1fc6a7a8,0xa1642800,0x27880000,0x9648a764,0xa7fe221f,
0x26dda62f,0xa41da513,0xa4c427a8,0x266d20a5,0xa7ea1e3e,0x9cb227d9,0x27c3a472,0x9fc6a6a7,0x255f238b,0x25eda70e,0xa73b9a46,0xa2d727f6,
0x9cb22800,0x27ea0000,0xa7c3221f,0x1fc62764,0x22d7a7a8,0xa73ba0a5,0x27fe9a46,0x1648a7f6,0xa55f26a7,0x25ed2472,0xa7889e3e,0xa16427d9,
0x26dda513,0xa41da62f,0x266d238b,0x24c4a70e,0x16482800,0x27fe0000,0x22d72764,0x273ba21f,0x9cb2a7f6,0xa7ea1a46,0xa41da70e,0xa6dd238b,
0x1fc627d9,0x27c39e3e,0x24c426a7,0x266da472,0xa164a7a8,0xa78820a5,0xa55fa62f,0xa5ed2513,0x1fc62800,0x27c30000,0x266da21f,0xa4c4a764,
0xa55fa70e,0xa5ed238b,0xa2d7262f,0x273b2513,0x27882472,0x2164a6a7,0x9648a7d9,0xa7fe9e3e,0xa7ea9a46,0x1cb227f6,0x241d27a8,0x26dda0a5,
0x22d72800,0x273b0000,0xa5eda764,0xa55f221f,0xa7c3a513,0x9fc6262f,0x27ea20a5,0x9cb2a7a8,0x266d9e3e,0xa4c4a7d9,0xa41d2472,0x26dd26a7,
0x9648270e,0x27fe238b,0xa164a7f6,0xa7889a46,0x24c42800,0x266d0000,0xa41d221f,0x26dd2764,0xa788a0a5,0x216427a8,0xa55fa7f6,0xa5ed1a46,
0x9648a6a7,0xa7fea472,0x273b1e3e,0xa2d7a7d9,0x27c3262f,0x1fc6a513,0x1cb2270e,0x27ea238b,0x25ed2800,0x255f0000,0x27882764,0x2164a21f,
0xa4c41a46,0x266d27f6,0x9fc6238b,0x27c3270e,0xa6dda7d9,0xa41d1e3e,0xa7eaa6a7,0x9cb22472,0x22d7a0a5,0xa73ba7a8,0x1648a513,0xa7fea62f,
0x26dd2800,0x241d0000,0x1cb2a21f,0xa7eaa764,0x9648238b,0x27fe270e,0x27882513,0xa164a62f,0xa73ba472,0x22d726a7,0x25ed27d9,0x255f1e3e,
0xa66da7f6,0xa4c49a46,0x9fc620a5,0x27c327a8,0x27882800,0x21640000,0xa7fea764,0x1648221f,0x241d262f,0x26dd2513,0xa66da7a8,0xa4c4a0a5,
0x9cb21e3e,0x27ea27d9,0x9fc6a472,0xa7c3a6a7,0xa5eda38b,0x255f270e,0x22d71a46,0xa73ba7f6,0x27ea2800,0x1cb20000,0x1fc6221f,0x27c32764,
0x273b27a8,0x22d720a5,0x96481a46,0x27fe27f6,0x25ed26a7,0x255f2472,0xa1649e3e,0x278827d9,0x241d2513,0x26dd262f,0xa4c4a38b,0x266d270e,
0x255f25a8,0xa5eda5a8,0x2164221f,0xa788a764,0x24c42513,0xa66da62f,0x1fc620a5,0xa7c3a7a8,0x241d2472,0xa6dda6a7,0x1cb21e3e,0xa7eaa7d9,
0x22d7238b,0xa73ba70e,0x16481a46,0xa7fea7f6,0xa41da5a8,0x26dd25a8,0x27ea2764,0x1cb2221f,0x9648a0a5,0x27fe27a8,0x278827f6,0xa1649a46,
0x22d71e3e,0x273b27d9,0x255f26a7,0xa5eda472,0x266d2513,0x24c4262f,0x1fc6238b,0xa7c3a70e,0x216425a8,0xa788a5a8,0x1648a21f,0x27fe2764,
0xa41d9a46,0xa6dda7f6,0x266d238b,0x24c4270e,0xa7eaa6a7,0x9cb2a472,0x27c327d9,0x9fc61e3e,0xa5eda7a8,0x255f20a5,0x22d7262f,0xa73ba513,
0x9cb2a5a8,0x27ea25a8,0xa7c3a764,0x1fc6a21f,0x273b238b,0x22d7270e,0x9648a513,0x27fe262f,0x255f27d9,0xa5ed9e3e,0x27882472,0x216426a7,
0xa41d1a46,0xa6dda7f6,0x24c427a8,0xa66da0a5,0x964825a8,0xa7fea5a8,0xa2d7221f,0xa73ba764,0xa7eaa62f,0x1cb2a513,0xa6dda7a8,0x241da0a5,
0x1fc6a472,0x27c326a7,0x24c49e3e,0x266d27d9,0x2788270e,0xa164238b,0x25ed27f6,0xa55f1a46,0x1fc6a5a8,0x27c325a8,0x266d2764,0xa4c4221f,
0x25ed27a8,0xa55f20a5,0xa73b9a46,0xa2d7a7f6,0xa7889e3e,0xa164a7d9,0x1648a6a7,0x27fe2472,0x1cb2a62f,0x27ea2513,0x26dd270e,0xa41d238b,
0xa2d725a8,0xa73ba5a8,0x25eda21f,0x255f2764,0x9fc6a7f6,0x27c31a46,0x9cb2270e,0xa7eaa38b,0x266d26a7,0xa4c42472,0xa41da7d9,0x26dd9e3e,
0xa7fea0a5,0x9648a7a8,0x27882513,0xa164262f,0x24c4a5a8,0x266d25a8,0xa41da764,0x26dda21f,0xa164270e,0xa788a38b,0x25ed262f,0xa55f2513,
0x1648a7d9,0x27fe1e3e,0xa73ba472,0x22d7a6a7,0x1fc627f6,0xa7c31a46,0x27ea20a5,0x9cb227a8,0xa5ed25a8,0xa55fa5a8,0xa788221f,0xa164a764,
0x266da513,0x24c4262f,0x27c3a0a5,0x1fc627a8,0xa6dd2472,0xa41da6a7,0xa7ea1e3e,0x9cb2a7d9,0x273ba38b,0x22d7270e,0x27fe9a46,0x164827f6,
0x26dda5a8,0x241d25a8,0x1cb22764,0xa7ea221f,0xa7fe20a5,0x9648a7a8,0x2164a7f6,0x27881a46,0x273b1e3e,0xa2d727d9,0xa5ed26a7,0xa55fa472,
0xa4c4a513,0x266da62f,0x27c3a38b,0x1fc6270e,0xa78825a8,0xa164a5a8,0x27fea21f,0x96482764,0x26dd1a46,0xa41d27f6,0xa4c4a38b,0x266da70e,
0x9cb2a6a7,0x27eaa472,0x9fc627d9,0xa7c31e3e,0xa55f27a8,0xa5eda0a5,0x273ba62f,0x22d72513,0x27eaa5a8,0x1cb225a8,0x1fc6a764,0x27c3a21f,
0xa2d7a38b,0x273ba70e,0xa7fe2513,0x9648a62f,0xa5ed27d9,0xa55f9e3e,0x21642472,0xa78826a7,0x26dd9a46,0xa41d27f6,0x266da7a8,0x24c420a5,
0xa7fe25a8,0x1648a5a8,0xa73b221f,0x22d7a764,0x9cb2262f,0xa7ea2513,0xa41d27a8,0xa6dd20a5,0x27c3a472,0x9fc626a7,0x266d9e3e,0xa4c427d9,
0x2164a70e,0x2788a38b,0x255fa7f6,0x25ed9a46,0x27c3a5a8,0x9fc625a8,0xa4c42764,0xa66d221f,0x255fa7a8,0x25eda0a5,0x22d71a46,0xa73b27f6,
0xa1649e3e,0x2788a7d9,0x27fea6a7,0x96482472,0xa7ea262f,0x1cb2a513,0x241da70e,0x26dda38b,0xa73b25a8,0x22d7a5a8,0x255fa21f,0xa5ed2764,
0xa7c327f6,0x9fc69a46,0x27eaa70e,0x9cb2238b,0xa4c426a7,0xa66d2472,0x26dda7d9,0x241d9e3e,0x164820a5,0xa7fe27a8,0x2164a513,0x2788a62f,
0x266da5a8,0xa4c425a8,0x26dda764,0x241da21f,0x2788a70e,0xa164238b,0x255fa62f,0x25eda513,0x27fea7d9,0x96481e3e,0x22d7a472,0x273ba6a7,
0x27c3a7f6,0x1fc69a46,0x1cb2a0a5,0x27eaa7a8,0xa55f25a8,0x25eda5a8,0xa164221f,0x2788a764,0xa4c42513,0x266da62f,0x9fc620a5,0x27c3a7a8,
0xa41d2472,0x26dda6a7,0x9cb21e3e,0x27eaa7d9,0xa2d7238b,0x273ba70e,0x96481a46,0x27fea7f6,0x241da5a8,0xa6dd25a8,0xa7ea2764,0x9cb2221f,
0x1648a0a5,0xa7fe27a8,0xa78827f6,0x21649a46,0xa2d71e3e,0xa73b27d9,0xa55f26a7,0x25eda472,0xa66d2513,0xa4c4262f,0x9fc6238b,0x27c3a70e,
0xa16425a8,0x2788a5a8,0x9648a21f,0xa7fe2764,0x241d9a46,0x26dda7f6,0xa66d238b,0xa4c4270e,0x27eaa6a7,0x1cb2a472,0xa7c327d9,0x1fc61e3e,
0x25eda7a8,0xa55f20a5,0xa2d7262f,0x273ba513,0x1cb2a5a8,0xa7ea25a8,0x27c3a764,0x9fc6a21f,0xa73b238b,0xa2d7270e,0x1648a513,0xa7fe262f,
0xa55f27d9,0x25ed9e3e,0xa7882472,0xa16426a7,0x241d1a46,0x26dda7f6,0xa4c427a8,0x266da0a5,0x164825a8,0x27fea5a8,0x22d7221f,0x273ba764,
0x27eaa62f,0x9cb2a513,0x26dda7a8,0xa41da0a5,0x9fc6a472,0xa7c326a7,0xa4c49e3e,0xa66d27d9,0xa788270e,0x2164238b,0xa5ed27f6,0x255f1a46,
0x9fc6a5a8,0xa7c325a8,0xa66d2764,0x24c4221f,0xa5ed27a8,0x255f20a5,0x273b9a46,0x22d7a7f6,0x27889e3e,0x2164a7d9,0x9648a6a7,0xa7fe2472,
0x9cb2a62f,0xa7ea2513,0xa6dd270e,0x241d238b,0x22d725a8,0x273ba5a8,0xa5eda21f,0xa55f2764,0x1fc6a7f6,0xa7c31a46,0x1cb2270e,0x27eaa38b,
0xa66d26a7,0x24c42472,0x241da7d9,0xa6dd9e3e,0x27fea0a5,0x1648a7a8,0xa7882513,0x2164262f,0xa4c4a5a8,0xa66d25a8,0x241da764,0xa6dda21f,
0x2164270e,0x2788a38b,0xa5ed262f,0x255f2513,0x9648a7d9,0xa7fe1e3e,0x273ba472,0xa2d7a6a7,0x9fc627f6,0x27c31a46,0xa7ea20a5,0x1cb227a8,
0x25ed25a8,0x255fa5a8,0x2788221f,0x2164a764,0xa66da513,0xa4c4262f,0xa7c3a0a5,0x9fc627a8,0x26dd2472,0x241da6a7,0x27ea1e3e,0x1cb2a7d9,
0xa73ba38b,0xa2d7270e,0xa7fe9a46,0x964827f6,0xa6dda5a8,0xa41d25a8,0x9cb22764,0x27ea221f,0x27fe20a5,0x1648a7a8,0xa164a7f6,0xa7881a46,
0xa73b1e3e,0x22d727d9,0x25ed26a7,0x255fa472,0x24c4a513,0xa66da62f,0xa7c3a38b,0x9fc6270e,0x278825a8,0x2164a5a8,0xa7fea21f,0x16482764,
0xa6dd1a46,0x241d27f6,0x24c4a38b,0xa66da70e,0x1cb2a6a7,0xa7eaa472,0x1fc627d9,0x27c31e3e,0x255f27a8,0x25eda0a5,0xa73ba62f,0xa2d72513,
0xa7eaa5a8,0x9cb225a8,0x9fc6a764,0xa7c3a21f,0x22d7a38b,0xa73ba70e,0x27fe2513,0x1648a62f,0x25ed27d9,0x255f9e3e,0xa1642472,0x278826a7,
0xa6dd9a46,0x241d27f6,0xa66da7a8,0xa4c420a5,0x27fe25a8,0x9648a5a8,0x273b221f,0xa2d7a764,0x1cb2262f,0x27ea2513,0x241d27a8,0x26dd20a5,
0xa7c3a472,0x1fc626a7,0xa66d9e3e,0x24c427d9,0xa164a70e,0xa788a38b,0xa55fa7f6,0xa5ed9a46,0xa7c3a5a8,0x1fc625a8,0x24c42764,0x266d221f,
0xa55fa7a8,0xa5eda0a5,0xa2d71a46,0x273b27f6,0x21649e3e,0xa788a7d9,0xa7fea6a7,0x16482472,0x27ea262f,0x9cb2a513,0xa41da70e,0xa6dda38b,
0x273b25a8,0xa2d7a5a8,0xa55fa21f,0x25ed2764,0x27c327f6,0x1fc69a46,0xa7eaa70e,0x1cb2238b,0x24c426a7,0x266d2472,0xa6dda7d9,0xa41d9e3e,
0x964820a5,0x27fe27a8,0xa164a513,0xa788a62f,0xa66da5a8,0x24c425a8,0xa6dda764,0xa41da21f,0xa788a70e,0x2164238b,0xa55fa62f,0xa5eda513,
0xa7fea7d9,0x16481e3e,0xa2d7a472,0xa73ba6a7,0xa7c3a7f6,0x9fc69a46,0x9cb2a0a5,0xa7eaa7a8,
};

#define PROF(slot) do {} while (0)
#define PROF3(slot) do {} while (0)
#define PROF2(slot) do {} while (0)

__device__ __forceinline__ uint32_t smem_u32(const void* p) { return (uint32_t)__cvta_generic_to_shared(p); }

__device__ __forceinline__ void mbar_init(uint32_t a, uint32_t c) {
  asm volatile("mbarrier.init.shared::cta.b64 [%0], %1;\n" ::"r"(a), "r"(c) : "memory");
}
__device__ __forceinline__ void mbar_expect_tx(uint32_t a, uint32_t bytes) {
  asm volatile("mbarrier.arrive.expect_tx.shared::cta.b64 _, [%0], %1;\n" ::"r"(a), "r"(bytes) : "memory");
}
__device__ __forceinline__ void mbar_arrive_cluster(uint32_t cluster_addr) {
  asm volatile("mbarrier.arrive.shared::cluster.b64 _, [%0];\n" ::"r"(cluster_addr) : "memory");
}
__device__ __forceinline__ void mbar_arrive_cluster_n(uint32_t cluster_addr, uint32_t n) {
  asm volatile("mbarrier.arrive.shared::cluster.b64 _, [%0], %1;\n" ::"r"(cluster_addr), "r"(n) : "memory");
}
__device__ __forceinline__ bool mbar_try(uint32_t a, uint32_t parity) {
  uint32_t ok;
  asm volatile("{\n.reg .pred p;\nmbarrier.try_wait.parity.shared::cta.b64 p, [%1], %2;\nselp.u32 %0, 1, 0, p;\n}\n"
               : "=r"(ok) : "r"(a), "r"(parity) : "memory");
  return ok;
}
__device__ __forceinline__ void mbar_wait(uint32_t a, uint32_t parity) {
  if (mbar_try(a, parity)) return;
#pragma unroll 1
  for (int n = 0; n < SPIN_LIMIT; n++)
    if (mbar_try(a, parity)) break;
}
__device__ __forceinline__ void mbar_wait_idle(uint32_t a, uint32_t parity) {
#pragma unroll 1
  for (int n = 0; n < SPIN_LIMIT; n++) {
    uint32_t ok;
    asm volatile("{\n.reg .pred p;\nmbarrier.try_wait.parity.shared::cta.b64 p, [%1], %2, %3;\nselp.u32 %0, 1, 0, p;\n}\n"
                 : "=r"(ok) : "r"(a), "r"(parity), "r"(4000) : "memory");
    if (ok) break;
  }
}
__device__ __forceinline__ bool elect_one() {
  uint32_t p;
  asm volatile("{\n.reg .pred P;\nelect.sync _|P, 0xffffffff;\nselp.u32 %0, 1, 0, P;\n}\n" : "=r"(p));
  return p;
}
__device__ __forceinline__ uint32_t mapa(uint32_t a, uint32_t rank) {
  uint32_t r;
  asm volatile("mapa.shared::cluster.u32 %0, %1, %2;\n" : "=r"(r) : "r"(a), "r"(rank));
  return r;
}
__device__ __forceinline__ void nb_sync(int id, int n) { asm volatile("bar.sync %0, %1;\n" ::"r"(id), "r"(n) : "memory"); }
__device__ __forceinline__ void nb_arrive(int id, int n) { asm volatile("bar.arrive %0, %1;\n" ::"r"(id), "r"(n) : "memory"); }
__device__ __forceinline__ void cluster_sync_all() {
  asm volatile("barrier.cluster.arrive.relaxed.aligned;\nbarrier.cluster.wait.aligned;\n" ::: "memory");
}
__device__ __forceinline__ void fence_async_smem() { asm volatile("fence.proxy.async.shared::cta;\n" ::: "memory"); }
__device__ __forceinline__ void fence_async_all() { asm volatile("fence.proxy.async.global;\n" ::: "memory"); }

__device__ __forceinline__ void tma_load_3d(uint32_t dst, const CUtensorMap* tm, uint32_t bar, int c0, int c1, int c2) {
  asm volatile(
      "cp.async.bulk.tensor.3d.shared::cluster.global.mbarrier::complete_tx::bytes [%0], [%1, {%3, %4, %5}], [%2];\n"
      ::"r"(dst), "l"(tm), "r"(bar), "r"(c0), "r"(c1), "r"(c2) : "memory");
}
__device__ __forceinline__ void tma_load_4d(uint32_t dst, const CUtensorMap* tm, uint32_t bar, int c0, int c1, int c2, int c3) {
  asm volatile(
      "cp.async.bulk.tensor.4d.shared::cluster.global.mbarrier::complete_tx::bytes [%0], [%1, {%3, %4, %5, %6}], [%2];\n"
      ::"r"(dst), "l"(tm), "r"(bar), "r"(c0), "r"(c1), "r"(c2), "r"(c3) : "memory");
}
__device__ __forceinline__ void tma_load_3d_mc(uint32_t dst, const CUtensorMap* tm, uint32_t bar, int c0, int c1, int c2) {
  asm volatile(
      "cp.async.bulk.tensor.3d.shared::cluster.global.mbarrier::complete_tx::bytes.multicast::cluster [%0], [%1, {%3, %4, %5}], [%2], %6;\n"
      ::"r"(dst), "l"(tm), "r"(bar), "r"(c0), "r"(c1), "r"(c2), "h"((uint16_t)3) : "memory");
}
__device__ __forceinline__ void tma_load_5d(uint32_t dst, const CUtensorMap* tm, uint32_t bar, int c0, int c4) {
  asm volatile(
      "cp.async.bulk.tensor.5d.shared::cluster.global.mbarrier::complete_tx::bytes [%0], [%1, {%3, %5, %5, %5, %4}], [%2];\n"
      ::"r"(dst), "l"(tm), "r"(bar), "r"(c0), "r"(c4), "r"(0) : "memory");
}
__device__ __forceinline__ void bulk_load(uint32_t dst, const void* src, uint32_t bytes, uint32_t bar) {
  asm volatile("cp.async.bulk.shared::cluster.global.mbarrier::complete_tx::bytes [%0], [%1], %2, [%3];\n"
               ::"r"(dst), "l"(src), "r"(bytes), "r"(bar) : "memory");
}
__device__ __forceinline__ void bulk_commit() { asm volatile("cp.async.bulk.commit_group;\n" ::: "memory"); }
__device__ __forceinline__ void bulk_wait0() { asm volatile("cp.async.bulk.wait_group 0;\n" ::: "memory"); }
__device__ __forceinline__ void prefetch_tmap(const CUtensorMap* tm) {
  asm volatile("prefetch.tensormap [%0];\n" ::"l"(tm) : "memory");
}

__device__ __forceinline__ void wg_fence() { asm volatile("wgmma.fence.sync.aligned;\n" ::: "memory"); }
__device__ __forceinline__ void wg_commit() { asm volatile("wgmma.commit_group.sync.aligned;\n" ::: "memory"); }
template <int N> __device__ __forceinline__ void wg_wait() {
  asm volatile("wgmma.wait_group.sync.aligned %0;\n" ::"n"(N) : "memory");
}
__device__ __forceinline__ uint64_t mkdesc(uint32_t addr, uint32_t lbo, uint32_t sbo, uint32_t swz) {
  return (uint64_t)((addr & 0x3FFFF) >> 4) | ((uint64_t)(lbo >> 4) << 16) | ((uint64_t)(sbo >> 4) << 32) |
         ((uint64_t)swz << 62);
}

#define R4(d, o) "+f"(d[o + 0]), "+f"(d[o + 1]), "+f"(d[o + 2]), "+f"(d[o + 3])
#define R8(d, o) R4(d, o), R4(d, o + 4)
#define R16(d, o) R8(d, o), R8(d, o + 8)
#define R32(d, o) R16(d, o), R16(d, o + 16)
#define R64(d, o) R32(d, o), R32(d, o + 32)

__device__ __forceinline__ void wgmma_n192(float (&d)[96], uint64_t da, uint64_t db, uint32_t acc) {
  asm volatile(
      "{\n.reg .pred p;\nsetp.ne.u32 p, %98, 0;\n"
      "wgmma.mma_async.sync.aligned.m64n192k16.f32.bf16.bf16 "
      "{%0,%1,%2,%3,%4,%5,%6,%7,%8,%9,%10,%11,%12,%13,%14,%15,%16,%17,%18,%19,%20,%21,%22,%23,%24,%25,%26,%27,%28,%29,%30,%31,"
      "%32,%33,%34,%35,%36,%37,%38,%39,%40,%41,%42,%43,%44,%45,%46,%47,%48,%49,%50,%51,%52,%53,%54,%55,%56,%57,%58,%59,%60,%61,%62,%63,"
      "%64,%65,%66,%67,%68,%69,%70,%71,%72,%73,%74,%75,%76,%77,%78,%79,%80,%81,%82,%83,%84,%85,%86,%87,%88,%89,%90,%91,%92,%93,%94,%95}, "
      "%96, %97, p, 1, 1, 0, 1;\n}\n"
      : R64(d, 0), R32(d, 64)
      : "l"(da), "l"(db), "r"(acc));
}
__device__ __forceinline__ void wgmma_n128(float (&d)[64], uint64_t da, uint64_t db, uint32_t acc) {
  asm volatile(
      "{\n.reg .pred p;\nsetp.ne.u32 p, %66, 0;\n"
      "wgmma.mma_async.sync.aligned.m64n128k16.f32.bf16.bf16 "
      "{%0,%1,%2,%3,%4,%5,%6,%7,%8,%9,%10,%11,%12,%13,%14,%15,%16,%17,%18,%19,%20,%21,%22,%23,%24,%25,%26,%27,%28,%29,%30,%31,"
      "%32,%33,%34,%35,%36,%37,%38,%39,%40,%41,%42,%43,%44,%45,%46,%47,%48,%49,%50,%51,%52,%53,%54,%55,%56,%57,%58,%59,%60,%61,%62,%63}, "
      "%64, %65, p, 1, 1, 0, 1;\n}\n"
      : R64(d, 0)
      : "l"(da), "l"(db), "r"(acc));
}
template <int N> __device__ __forceinline__ void fence_regs(float (&d)[N]) {
#pragma unroll
  for (int i = 0; i < N; i++) asm volatile("" : "+f"(d[i])::"memory");
}

__device__ __forceinline__ void mma16816(float (&d)[4], uint32_t a0, uint32_t a1, uint32_t a2, uint32_t a3, uint32_t b0,
                                         uint32_t b1) {
  asm("mma.sync.aligned.m16n8k16.row.col.f32.bf16.bf16.f32 {%0,%1,%2,%3}, {%4,%5,%6,%7}, {%8,%9}, {%0,%1,%2,%3};\n"
      : "+f"(d[0]), "+f"(d[1]), "+f"(d[2]), "+f"(d[3])
      : "r"(a0), "r"(a1), "r"(a2), "r"(a3), "r"(b0), "r"(b1));
}
__device__ __forceinline__ void mma16816_z(float (&d)[4], uint32_t a0, uint32_t a1, uint32_t a2, uint32_t a3, uint32_t b0,
                                           uint32_t b1) {
  asm("mma.sync.aligned.m16n8k16.row.col.f32.bf16.bf16.f32 {%0,%1,%2,%3}, {%4,%5,%6,%7}, {%8,%9}, {%10,%10,%10,%10};\n"
      : "=f"(d[0]), "=f"(d[1]), "=f"(d[2]), "=f"(d[3])
      : "r"(a0), "r"(a1), "r"(a2), "r"(a3), "r"(b0), "r"(b1), "f"(0.f));
}
__device__ __forceinline__ void ldsm4t(uint32_t (&r)[4], uint32_t a) {
  asm volatile("ldmatrix.sync.aligned.m8n8.x4.trans.shared.b16 {%0,%1,%2,%3}, [%4];\n"
               : "=r"(r[0]), "=r"(r[1]), "=r"(r[2]), "=r"(r[3]) : "r"(a) : "memory");
}
__device__ __forceinline__ void ldsm2t(uint32_t& r0, uint32_t& r1, uint32_t a) {
  asm volatile("ldmatrix.sync.aligned.m8n8.x2.trans.shared.b16 {%0,%1}, [%2];\n" : "=r"(r0), "=r"(r1) : "r"(a) : "memory");
}
__device__ __forceinline__ void st_async128(uint32_t a, uint32_t bar, uint32_t x, uint32_t y, uint32_t z, uint32_t w) {
  asm volatile("st.async.weak.shared::cluster.mbarrier::complete_tx::bytes.v4.b32 [%0], {%2,%3,%4,%5}, [%1];\n"
               ::"r"(a), "r"(bar), "r"(x), "r"(y), "r"(z), "r"(w) : "memory");
}
__device__ __forceinline__ void mbar_arrive(uint32_t a) {
  asm volatile("mbarrier.arrive.shared::cta.b64 _, [%0];\n" ::"r"(a) : "memory");
}
__device__ __forceinline__ void stsm4(uint32_t a, uint32_t r0, uint32_t r1, uint32_t r2, uint32_t r3) {
  asm volatile("stmatrix.sync.aligned.m8n8.x4.shared.b16 [%0], {%1,%2,%3,%4};\n"
               ::"r"(a), "r"(r0), "r"(r1), "r"(r2), "r"(r3) : "memory");
}
__device__ __forceinline__ void stsm4t(uint32_t a, uint32_t r0, uint32_t r1, uint32_t r2, uint32_t r3) {
  asm volatile("stmatrix.sync.aligned.m8n8.x4.trans.shared.b16 [%0], {%1,%2,%3,%4};\n"
               ::"r"(a), "r"(r0), "r"(r1), "r"(r2), "r"(r3) : "memory");
}
__device__ __forceinline__ uint2 lds64(uint32_t a) {
  uint2 v;
  asm volatile("ld.shared.v2.u32 {%0,%1}, [%2];\n" : "=r"(v.x), "=r"(v.y) : "r"(a));
  return v;
}
__device__ __forceinline__ uint4 lds128(uint32_t a) {
  uint4 v;
  asm volatile("ld.shared.v4.u32 {%0,%1,%2,%3}, [%4];\n" : "=r"(v.x), "=r"(v.y), "=r"(v.z), "=r"(v.w) : "r"(a) : "memory");
  return v;
}
__device__ __forceinline__ void sts128(uint32_t a, uint32_t x, uint32_t y, uint32_t z, uint32_t w) {
  asm volatile("st.shared.v4.u32 [%0], {%1,%2,%3,%4};\n" ::"r"(a), "r"(x), "r"(y), "r"(z), "r"(w) : "memory");
}
__device__ __forceinline__ uint32_t pack_bf16(float lo, float hi) {
  uint32_t r;
  asm("cvt.rn.bf16x2.f32 %0, %1, %2;\n" : "=r"(r) : "f"(hi), "f"(lo));
  return r;
}
__device__ __forceinline__ uint32_t bmul2(uint32_t a, uint32_t b) {
  uint32_t r;
  asm("mul.rn.bf16x2 %0, %1, %2;\n" : "=r"(r) : "r"(a), "r"(b));
  return r;
}
__device__ __forceinline__ uint32_t bmax2(uint32_t a, uint32_t b) {
  uint32_t r;
  asm("max.bf16x2 %0, %1, %2;\n" : "=r"(r) : "r"(a), "r"(b));
  return r;
}
__device__ __forceinline__ uint32_t bfma2(uint32_t a, uint32_t b, uint32_t c) {
  uint32_t r;
  asm("fma.rn.bf16x2 %0, %1, %2, %3;\n" : "=r"(r) : "r"(a), "r"(b), "r"(c));
  return r;
}
__device__ __forceinline__ uint32_t badd2(uint32_t a, uint32_t b) {
  uint32_t r;
  asm("add.rn.bf16x2 %0, %1, %2;\n" : "=r"(r) : "r"(a), "r"(b));
  return r;
}
__device__ __forceinline__ void prefetch_l2(const void* p) { asm volatile("prefetch.global.L2 [%0];\n" ::"l"(p)); }
__device__ __forceinline__ void cp_async16n(uint32_t dst, const void* src) {
  asm volatile("cp.async.cg.shared.global [%0], [%1], 16;\n" ::"r"(dst), "l"(src) : "memory");
}
__device__ __forceinline__ void cp_async16(uint32_t dst, const void* src, uint32_t srcbytes) {
  asm volatile("cp.async.cg.shared.global.L2::256B [%0], [%1], 16, %2;\n" ::"r"(dst), "l"(src), "r"(srcbytes) : "memory");
}
__device__ __forceinline__ uint32_t ld_acquire(const uint32_t* p) {
  uint32_t v;
  asm volatile("ld.acquire.gpu.global.u32 %0, [%1];\n" : "=r"(v) : "l"(p) : "memory");
  return v;
}
__device__ __forceinline__ uint32_t ld_relaxed(const uint32_t* p) {
  uint32_t v;
  asm volatile("ld.relaxed.gpu.global.u32 %0, [%1];\n" : "=r"(v) : "l"(p) : "memory");
  return v;
}
__device__ __forceinline__ void st_release(uint32_t* p, uint32_t v) {
  asm volatile("st.release.gpu.global.u32 [%0], %1;\n" ::"l"(p), "r"(v) : "memory");
}
__device__ __forceinline__ void wait_flag(const uint32_t* p, uint32_t want) {
  int n = 0;
  while (ld_relaxed(p) != want && ++n < SPIN_LIMIT) __nanosleep(40);
  (void)ld_acquire(p);
}

struct Params {
  const __nv_bfloat16* x;
  const __nv_bfloat16* w;
  const __nv_bfloat16* q;
  const __nv_bfloat16* k;
  const __nv_bfloat16* v;
  const __nv_bfloat16* shift_k;
  const __nv_bfloat16* ssm_k;
  const __nv_bfloat16* ssm_D;
  const __nv_bfloat16* wo;
  __nv_bfloat16* out;
};

__device__ __forceinline__ uint32_t lds32(uint32_t a) {
  uint32_t v;
  asm volatile("ld.shared.u32 %0, [%1];\n" : "=r"(v) : "r"(a));
  return v;
}
#define W4(d, o) "=f"(d[o + 0]), "=f"(d[o + 1]), "=f"(d[o + 2]), "=f"(d[o + 3])
#define W8(d, o) W4(d, o), W4(d, o + 4)
#define W16(d, o) W8(d, o), W8(d, o + 8)
#define U4(c, d, o) c(d[o + 0]), c(d[o + 1]), c(d[o + 2]), c(d[o + 3])
#define U8(c, d, o) U4(c, d, o), U4(c, d, o + 4)
#define U16(c, d, o) U8(c, d, o), U8(c, d, o + 8)
#define U32(c, d, o) U16(c, d, o), U16(c, d, o + 16)
#define D32 "{%0,%1,%2,%3,%4,%5,%6,%7,%8,%9,%10,%11,%12,%13,%14,%15,%16,%17,%18,%19,%20,%21,%22,%23,%24,%25,%26,%27,%28,%29,%30,%31}"
#define D16 "{%0,%1,%2,%3,%4,%5,%6,%7,%8,%9,%10,%11,%12,%13,%14,%15}"
#define D8 "{%0,%1,%2,%3,%4,%5,%6,%7}"
template <int ACC> __device__ __forceinline__ void hmma_n128t(uint32_t (&d)[32], const uint32_t (&a)[4], uint64_t db) {
  if (ACC)
    asm volatile("wgmma.mma_async.sync.aligned.m64n128k16.f16.f16.f16 " D32 ", {%32,%33,%34,%35}, %36, 1, 1, 1, 1;\n"
                 : U32("+r", d, 0) : "r"(a[0]), "r"(a[1]), "r"(a[2]), "r"(a[3]), "l"(db));
  else
    asm volatile("wgmma.mma_async.sync.aligned.m64n128k16.f16.f16.f16 " D32 ", {%32,%33,%34,%35}, %36, 0, 1, 1, 1;\n"
                 : U32("=r", d, 0) : "r"(a[0]), "r"(a[1]), "r"(a[2]), "r"(a[3]), "l"(db));
}
template <int ACC, int TB> __device__ __forceinline__ void hmma_n32(uint32_t (&d)[8], const uint32_t (&a)[4], uint64_t db) {
  if (ACC)
    asm volatile("wgmma.mma_async.sync.aligned.m64n32k16.f16.f16.f16 " D8 ", {%8,%9,%10,%11}, %12, 1, 1, 1, %13;\n"
                 : U8("+r", d, 0) : "r"(a[0]), "r"(a[1]), "r"(a[2]), "r"(a[3]), "l"(db), "n"(TB));
  else
    asm volatile("wgmma.mma_async.sync.aligned.m64n32k16.f16.f16.f16 " D8 ", {%8,%9,%10,%11}, %12, 0, 1, 1, %13;\n"
                 : U8("=r", d, 0) : "r"(a[0]), "r"(a[1]), "r"(a[2]), "r"(a[3]), "l"(db), "n"(TB));
}
template <int N> __device__ __forceinline__ void fence_regs(uint32_t (&d)[N]) {
#pragma unroll
  for (int i = 0; i < N; i++) asm volatile("" : "+r"(d[i])::"memory");
}
__device__ __forceinline__ uint32_t hmul(uint32_t a, uint32_t b) { uint32_t r; asm("mul.rn.f16x2 %0, %1, %2;\n" : "=r"(r) : "r"(a), "r"(b)); return r; }
__device__ __forceinline__ uint32_t hadd(uint32_t a, uint32_t b) { uint32_t r; asm("add.rn.f16x2 %0, %1, %2;\n" : "=r"(r) : "r"(a), "r"(b)); return r; }
__device__ __forceinline__ uint32_t hsub(uint32_t a, uint32_t b) { uint32_t r; asm("sub.rn.f16x2 %0, %1, %2;\n" : "=r"(r) : "r"(a), "r"(b)); return r; }
__device__ __forceinline__ uint32_t hfma(uint32_t a, uint32_t b, uint32_t c) { uint32_t r; asm("fma.rn.f16x2 %0, %1, %2, %3;\n" : "=r"(r) : "r"(a), "r"(b), "r"(c)); return r; }
__device__ __forceinline__ uint32_t hfnma(uint32_t a, uint32_t b, uint32_t c) {
  uint32_t r;
  asm("{\n.reg .b32 t;\nneg.f16x2 t, %1;\nfma.rn.f16x2 %0, t, %2, %3;\n}\n" : "=r"(r) : "r"(a), "r"(b), "r"(c));
  return r;
}
__device__ __forceinline__ uint32_t hrefl(uint32_t p, uint32_t s) {
  uint32_t r;
  asm("{\n.reg .b32 t;\nneg.f16x2 t, %2;\nfma.rn.f16x2 %0, %1, %3, t;\n}\n" : "=r"(r) : "r"(p), "r"(s), "r"(0x40004000u));
  return r;
}
__device__ __forceinline__ void bfly(uint32_t xr, uint32_t xi, uint32_t tr, uint32_t ti, uint32_t yr, uint32_t yi, uint32_t ur,
                                     uint32_t ui, uint32_t& sr, uint32_t& si, uint32_t& dr, uint32_t& di) {
  const uint32_t pr = hfnma(xi, ti, hmul(xr, tr)), pi = hfma(xi, tr, hmul(xr, ti));
  sr = hfnma(yi, ui, hfma(yr, ur, pr));
  si = hfma(yi, ur, hfma(yr, ui, pi));
  dr = hrefl(pr, sr);
  di = hrefl(pi, si);
}
template <int BH> __device__ __forceinline__ void fft_e1(const uint32_t (&d)[32], const uint32_t (&tw)[16], uint32_t (&a2)[2][2][4]) {
#pragma unroll
  for (int be = 0; be < 2; be++)
#pragma unroll
    for (int s = 0; s < 2; s++) {
      const int o = 16 * s + 8 * be + 2 * BH, p = 2 * BH;
      bfly(d[o], d[o + 1], tw[p], tw[p + 1], d[o + 4], d[o + 5], tw[p + 4], tw[p + 5], a2[be][0][s], a2[be][0][2 + s],
           a2[be][1][s], a2[be][1][2 + s]);
    }
}
__device__ __forceinline__ uint32_t hfms(uint32_t a, uint32_t b, uint32_t c) {
  uint32_t r;
  asm("{\n.reg .b32 t;\nneg.f16x2 t, %3;\nfma.rn.f16x2 %0, %1, %2, t;\n}\n" : "=r"(r) : "r"(a), "r"(b), "r"(c));
  return r;
}
template <int C, int J> __device__ __forceinline__ void fft_e2(const uint32_t (&d0)[8], const uint32_t (&d1)[8], uint32_t (&a3)[2][4]) {
  const uint32_t ur = d0[2 * J], ui = d0[4 + 2 * J], hr = d0[2 * J + 1], hi = d0[5 + 2 * J];
  const uint32_t vr = d1[2 * J], vi = d1[4 + 2 * J], gr = d1[2 * J + 1], gi = d1[5 + 2 * J];
  const uint32_t pr = hfnma(ui, hi, hmul(ur, hr)), pi = hfma(ui, hr, hmul(ur, hi));
  a3[0][2 + C] = pr;
  a3[0][C] = pi;
  a3[1][2 + C] = hfnma(vi, hi, hfma(vr, hr, hfnma(ui, gi, hfms(ur, gr, pi))));
  a3[1][C] = hfma(vi, hr, hfma(vr, hi, hfma(ui, gr, hfma(ur, gi, pr))));
}
__device__ __forceinline__ void fft_e3(const uint32_t (&d)[2][8], const uint32_t (&tw)[16], uint32_t zaddr) {
#pragma unroll
  for (int rho = 0; rho < 2; rho++) {
    uint32_t zr[4], zi[4];
#pragma unroll
    for (int nb = 0; nb < 4; nb++) {
      const uint32_t xi = d[nb >> 1][2 * (nb & 1) + rho], xr = d[nb >> 1][4 + 2 * (nb & 1) + rho];
      const uint32_t tr = tw[8 + 4 * rho + 2 * (nb & 1)], ti = tw[9 + 4 * rho + 2 * (nb & 1)];
      zr[nb] = hfnma(xi, ti, hmul(xr, tr));
      zi[nb] = hfma(xi, tr, hmul(xr, ti));
    }
    stsm4(zaddr + rho * 1024, zr[0], zr[1], zr[2], zr[3]);
    stsm4(zaddr + rho * 1024 + 512, zi[0], zi[1], zi[2], zi[3]);
  }
}
__device__ __forceinline__ float bf_lo(uint32_t v) {
  uint32_t r;
  asm("prmt.b32 %0, %1, 0, 0x1044;\n" : "=r"(r) : "r"(v));
  return __uint_as_float(r);
}
__device__ __forceinline__ float bf_hi(uint32_t v) { return __uint_as_float(v & 0xffff0000u); }
__device__ __forceinline__ float ex2(float x) {
  float r;
  asm("ex2.approx.ftz.f32 %0, %1;\n" : "=f"(r) : "f"(x));
  return r;
}
__device__ __forceinline__ float rcp(float x) {
  float r;
  asm("rcp.approx.ftz.f32 %0, %1;\n" : "=f"(r) : "f"(x));
  return r;
}

__device__ __forceinline__ int g2_a(int s, int h) { return (((0xA1023 ^ (h * 0x11)) >> (4 * s)) & 15) * 16384; }
__device__ __forceinline__ int g2_b(int s) { return ((0xCDB54 >> (4 * s)) & 15) * 16384; }
static_assert(OFF_U == 10 * 16384 && OFF_H == 12 * 16384 && OFF_OP == 2 * 16384, "units");
__device__ __forceinline__ int g2_k(int hp, int i) {
  return i < 2 ? hp ^ 1 ^ i : i < 4 ? (hp & ~1) ^ i : ((hp & ~3) + i) & 15; }
__device__ __forceinline__ int y_slot(int wg, int it) {
  static_assert(T_B2 == T_TW + 8192 && T_A1 == T_B2 + 4096, "y slots");
  return OFF_T + T_TW + ((it + 3) & 3) * 4096 + wg * 2048;
}

__device__ __forceinline__ void to_arr(uint32_t (&d)[4], uint4 v) { d[0] = v.x; d[1] = v.y; d[2] = v.z; d[3] = v.w; }

__device__ __forceinline__ void attn_stage(uint32_t sb, int blk, int lane, const float (&acc)[96], uint32_t (&k1)[2][4]) {
  const int lr = lane & 7, lm = lane >> 3;
  const uint32_t base = sb + OFF_VP + (blk * 16 + lr + 8 * (lm & 1)) * 128;
#pragma unroll
  for (int i = 0; i < 8; i++) k1[i >> 2][i & 3] = pack_bf16(acc[34 + 4 * i], acc[35 + 4 * i]);
  const uint32_t kh = sb + OFF_OP + (blk + 1) * 2048 + lane * 16;
  if (blk < 15) {
    sts128(kh, k1[0][0], k1[0][1], k1[0][2], k1[0][3]);
    sts128(kh + 512, k1[1][0], k1[1][1], k1[1][2], k1[1][3]);
  }
#pragma unroll
  for (int j = 0; j < 8; j += 2)
    stsm4(base + (((j + (lm >> 1)) ^ lr) << 4), pack_bf16(acc[64 + 4 * j], acc[65 + 4 * j]),
          pack_bf16(acc[66 + 4 * j], acc[67 + 4 * j]), pack_bf16(acc[68 + 4 * j], acc[69 + 4 * j]),
          pack_bf16(acc[70 + 4 * j], acc[71 + 4 * j]));
}
__device__ __forceinline__ void attn_pack(const float (&acc)[96], uint32_t (&qa)[2][8], uint32_t (&k0)[2][4]) {
#pragma unroll
  for (int hd = 0; hd < 2; hd++) {
#pragma unroll
    for (int i = 0; i < 8; i++) {
      asm volatile("cvt.rn.bf16x2.f32 %0, %1, %2;\n" : "=r"(qa[hd][i]) : "f"(acc[16 * hd + 2 * i + 1]), "f"(acc[16 * hd + 2 * i]));
    }
#pragma unroll
    for (int i = 0; i < 4; i++) {
      asm volatile("cvt.rn.bf16x2.f32 %0, %1, %2;\n" : "=r"(k0[hd][i]) : "f"(acc[33 + 16 * hd + 4 * i]), "f"(acc[32 + 16 * hd + 4 * i]));
    }
  }
}
__device__ __forceinline__ void attn_own(const uint32_t (&k0)[2][4], const uint32_t (&k1)[2][4], bool le0, bool le1,
                                         const uint32_t (&qa)[2][8], float (&l)[2][4]) {
#pragma unroll
  for (int hd = 0; hd < 2; hd++) {
    float s0[4], s1[4];
    mma16816_z(s0, qa[hd][0], qa[hd][1], qa[hd][2], qa[hd][3], k0[hd][0], k0[hd][1]);
    mma16816_z(s1, qa[hd][0], qa[hd][1], qa[hd][2], qa[hd][3], k1[hd][0], k1[hd][1]);
    mma16816(s0, qa[hd][4], qa[hd][5], qa[hd][6], qa[hd][7], k0[hd][2], k0[hd][3]);
    mma16816(s1, qa[hd][4], qa[hd][5], qa[hd][6], qa[hd][7], k1[hd][2], k1[hd][3]);
    l[hd][0] = s0[0];
    l[hd][1] = s0[1];
    l[hd][2] = le0 ? s1[2] : s0[2];
    l[hd][3] = le1 ? s1[3] : s0[3];
  }
}
template <int N> __device__ __forceinline__ void quad_softmax(float (&x)[N][2], uint32_t (&pp)[N]) {
  const float c2 = 1.4426950408889634f;
  uint32_t q[N], mx[N / 2];
#pragma unroll
  for (int n = 0; n < N; n++) {
    const uint32_t r = pack_bf16(x[n][0], x[n][1]);
    q[n] = bfma2(r, 0x3e353e35u, bmul2(r, 0x379e379eu));
    x[n][0] = bf_lo(q[n]);
    x[n][1] = bf_hi(q[n]);
  }
#pragma unroll
  for (int n = 0; n < N / 2; n++)
    mx[n] = bmax2(__byte_perm(q[2 * n], q[2 * n + 1], 0x5410), __byte_perm(q[2 * n], q[2 * n + 1], 0x7632));
#pragma unroll
  for (int o = 1; o <= 2; o++)
#pragma unroll
    for (int n = 0; n < N / 2; n++) mx[n] = bmax2(mx[n], __shfl_xor_sync(0xffffffffu, mx[n], o));
  float m[N], t[N];
#pragma unroll
  for (int n = 0; n < N / 2; n++) {
    m[2 * n] = bf_lo(mx[n]);
    m[2 * n + 1] = bf_hi(mx[n]);
  }
#pragma unroll
  for (int n = 0; n < N; n++) {
    const float nm = -m[n] * c2;
    x[n][0] = ex2(fmaf(x[n][0], c2, nm));
    x[n][1] = ex2(fmaf(x[n][1], c2, nm));
    t[n] = x[n][0] + x[n][1];
  }
#pragma unroll
  for (int o = 1; o <= 2; o++)
#pragma unroll
    for (int n = 0; n < N; n++) t[n] += __shfl_xor_sync(0xffffffffu, t[n], o);
#pragma unroll
  for (int n = 0; n < N; n++) {
    const float inv = rcp(t[n]);
    pp[n] = pack_bf16(x[n][0] * inv, x[n][1] * inv);
  }
}
__device__ __forceinline__ void attn_pv(uint32_t dst, const uint32_t (&va)[4], const uint32_t (&vb)[4], uint32_t pp,
                                        uint32_t maskLE) {
  const uint32_t b0 = pp & ~maskLE, b1 = pp & maskLE;
  float oa[4], ob[4];
  mma16816_z(oa, va[0], va[1], va[2], va[3], b0, b1);
  mma16816_z(ob, vb[0], vb[1], vb[2], vb[3], b0, b1);
  stsm4t(dst, pack_bf16(oa[0], oa[1]), pack_bf16(oa[2], oa[3]), pack_bf16(ob[0], ob[1]), pack_bf16(ob[2], ob[3]));
}

template <int MODE>
__global__ void __cluster_dims__(2, 1, 1) __launch_bounds__(NTHREADS, 1)
fused_kernel(const Params p, const __grid_constant__ CUtensorMap tmX, const __grid_constant__ CUtensorMap tmW,
             const __grid_constant__ CUtensorMap tmWo,
             const __grid_constant__ CUtensorMap tmQ,
             const __grid_constant__ CUtensorMap tmXh, const __grid_constant__ CUtensorMap tmWh) {
  extern __shared__ __align__(1024) uint8_t smem[];
  const uint32_t sb = smem_u32(smem);
  const uint32_t bars = sb + OFF_BAR;
  const int tid = threadIdx.x, lane = tid & 31, warp = __shfl_sync(0xffffffffu, tid >> 5, 0);
  const int rank = blockIdx.x & 1;
  const bool halo_cta = blockIdx.x < 4;
  if (halo_cta && MODE != 0) return;
  int grp, mem;
  {
    const int t = (blockIdx.x >> 1) - 4, u = t - 32;
    const int q7 = (u * 37) >> 8;
    const bool lo = (unsigned)t < 32u, mid = (unsigned)u < 28u;
    grp = lo ? (t & 7) : (mid ? 1 + u - 7 * q7 : 0);
    mem = lo ? (t >> 3) : (mid ? 4 + q7 : (t < 0 ? t + 6 : t - 54));
  }
  const int rg = (grp >> 2) * 4 + (mem >> 1), hp = (grp & 3) * 4 + (mem & 1) * 2 + rank;
  const int rb2 = (grp >> 2) * 8 + mem, cb2 = (grp & 3) * 2 + rank;
  const int chb = grp * 16 + mem * 2 + rank;
  const int cta = rg * 16 + hp;
  const int par = rg >> 2, gidx = rg & 3;

  if (tid < 256 && !halo_cta && MODE != 2) {
    const int r = tid >> 3, c = tid & 7;
    const uint32_t so = r * 128 + ((c ^ (r & 7)) << 4);
    const __nv_bfloat16* wg0 = p.w + (size_t)r * (3 * DM) + hp * 64 + c * 8;
    const __nv_bfloat16* xg0 = p.x + (size_t)(2 * (gidx * 256 + r) + par) * DM + c * 8;
#pragma unroll
    for (int j = 0; j < 3; j++) cp_async16n(sb + OFF_1B + j * 4096 + so, wg0 + j * DM);
#pragma unroll
    for (int i = 0; i < 8; i++) cp_async16n(sb + i * 4096 + so, xg0 + (size_t)i * 64 * DM);
    asm volatile("cp.async.commit_group;\n" ::: "memory");
  }
  if (tid == 256) {
    prefetch_tmap(halo_cta ? &tmXh : &tmX);
#pragma unroll
    for (int i = 0; i < NS1B; i++) mbar_init(bars + 8 * (BAR_FULLB + i), 1);
#pragma unroll
    for (int i = 0; i < NS1A; i++) mbar_init(bars + 8 * (BAR_FULLA + i), 1);
    asm volatile("fence.mbarrier_init.release.cluster;\n" ::: "memory");
    if (!halo_cta && MODE != 2) {
      mbar_expect_tx(bars + 8 * (BAR_FULLB + 1), STG1B);
      tma_load_3d(sb + OFF_1B + 1 * STG1B, &tmW, bars + 8 * (BAR_FULLB + 1), hp * 64, 32, 0);
      mbar_expect_tx(bars + 8 * (BAR_FULLB + 2), STG1B);
      tma_load_3d(sb + OFF_1B + 2 * STG1B, &tmW, bars + 8 * (BAR_FULLB + 2), hp * 64, 64, 0);
    } else {
      prefetch_tmap(&tmWh);
    }
  } else if (tid == 288) {
#pragma unroll
    for (int i = 0; i < NS1A; i++) mbar_init(bars + 8 * (BAR_EMPTYA + i), 4);
#pragma unroll
    for (int i = 0; i < NS1B; i++) mbar_init(bars + 8 * (BAR_EMPTYB + i), 2);
    asm volatile("fence.mbarrier_init.release.cluster;\n" ::: "memory");
  } else if (tid == 320) {
#pragma unroll
    for (int i = 0; i < NS2; i++) {
      mbar_init(bars + 8 * (BAR_FULL2 + i), 1);
      mbar_init(bars + 8 * (BAR_EMPTY2 + i), 4);
    }
    mbar_init(bars + 8 * BAR_DEAD, 2);
    mbar_init(bars + 8 * (BAR_DEAD + 1), 2);
    mbar_init(bars + 8 * BAR_X, 2);
    mbar_init(bars + 8 * BAR_REL, 2);
    asm volatile("fence.mbarrier_init.release.cluster;\n" ::: "memory");
  } else if (tid == 352) {
    mbar_init(bars + 8 * BAR_T, 1);
    mbar_init(bars + 8 * BAR_UH, 3);
    mbar_init(bars + 8 * BAR_LFREE, 4);
    mbar_init(bars + 8 * BAR_LAND, 1);
    mbar_init(bars + 8 * BAR_U, 1);
    mbar_init(bars + 8 * BAR_Q, 1);
    mbar_init(bars + 8 * BAR_STG, 9);
    asm volatile("fence.mbarrier_init.release.cluster;\n" ::: "memory");
  }
  if (warp == 8) PROF2(23);
  cluster_sync_all();
  if (warp == 8) PROF2(24);

  if (warp >= 8) {
    const int hw = warp - 8;
    const int lr = lane & 7, lm = lane >> 3;
    auto g1_issue_a = [&](int j, int s) {
      const uint32_t fb = bars + 8 * (BAR_FULLA + s);
      mbar_expect_tx(fb, STG1A);
      tma_load_3d_mc(sb + s * STG1A + rank * 16384, &tmX, fb, j * 64, par, gidx * 256 + rank * 128);
    };
    auto g1_issue_b = [&](int kb, int s) {
      const uint32_t fb = bars + 8 * (BAR_FULLB + s);
      mbar_expect_tx(fb, STG1B);
      tma_load_3d(sb + OFF_1B + s * STG1B, &tmW, fb, hp * 64, kb * 32, 0);
    };
    asm volatile("setmaxnreg.dec.sync.aligned.u32 %0;\n" :: "n"(REG_HELP));

    if (halo_cta) {
      if (hw == 0) {
        int s = 0, ph = 1;
#pragma unroll 1
        for (int kb = 0; kb < 16; kb++) {
          mbar_wait(bars + 8 * (BAR_EMPTYB + s), ph);
          const uint32_t fb = bars + 8 * (BAR_FULLB + s), st = sb + s * STGH;
          if (elect_one()) {
            mbar_expect_tx(fb, STGH);
            tma_load_4d(st, &tmXh, fb, kb * 64, 248, 0, 0);
            tma_load_3d(st + 8192, &tmWh, fb, 0, kb * 64, 16 + blockIdx.x * 4);
            tma_load_3d(st + 8192 + 32768, &tmWh, fb, 0, kb * 64, 32 + blockIdx.x * 4);
          }
          if (++s == 3) { s = 0; ph ^= 1; }
        }
      }
      __syncwarp();
    } else if (hw == 0) {
      uint32_t epoch = 0;
      if (lane < (MODE == 2 ? NS2 : 2)) mbar_arrive_cluster_n(mapa(bars, rank) + 8 * (BAR_EMPTY2 + lane), 4);
      if (MODE != 2) {
      epoch = ld_relaxed(g_flag_o + 2 * cta) + 1;
      if (lane == 0) {
        mbar_expect_tx(bars + 8 * BAR_U, 32768);
        mbar_expect_tx(bars + 8 * BAR_LAND, 32768 + 64);
        mbar_expect_tx(bars + 8 * BAR_Q, 32768);
        mbar_expect_tx(bars + 8 * BAR_T, T_END);
      }
      {
        int sa = 1, pha = 1, sbb = 2, phb = 1;
#pragma unroll 1
        for (int kb = 2; kb < 32; kb++) {
          if (!(kb & 1)) {
            mbar_wait(bars + 8 * (BAR_EMPTYA + sa), pha);
            if (elect_one()) g1_issue_a(kb >> 1, sa);
            if (++sa == NS1A) { sa = 0; pha ^= 1; }
          }
          mbar_wait(bars + 8 * (BAR_EMPTYB + sbb), phb);
          if (kb > 2 && elect_one()) g1_issue_b(kb, sbb);
          __syncwarp();
          if (kb >= PF0 && kb < PF0 + 12)
            prefetch_l2((kb < PF0 + 8 ? p.q + (size_t)chb * 16384 + (kb - PF0) * 2048 : p.wo + (size_t)chb * 8192 + (kb - PF0 - 8) * 2048) + lane * 64);
          if (kb == 4) PROF2(27);
          if (kb == 1) PROF2(38);
          if (kb == 2) PROF2(39);
          if (++sbb == NS1B) { sbb = 0; phb ^= 1; }
        }
      }
      static_assert(32 % NS1B == 2 && (32 / NS1B) % 2 == 0 && OFF_Q == OFF_1B && 2 * STG1B == 6 * 4096, "slots / parity of these loads");
      const uint8_t* tab = reinterpret_cast<const uint8_t*>(g_tab);
      if (lane == 0) {
        prefetch_tmap(&tmWo);
        prefetch_tmap(&tmQ);
        bulk_load(sb + OFF_T + T_A1, tab + T_A1, T_END - T_A1, bars + 8 * BAR_T);
        mbar_wait(bars + 8 * (BAR_EMPTYB + 2), 1);
        tma_load_5d(sb + OFF_Q + 6 * 4096, &tmQ, bars + 8 * BAR_Q, (chb & ~1) * 8, rank * 32 + 24);
        tma_load_5d(sb + OFF_Q + 7 * 4096, &tmQ, bars + 8 * BAR_Q, (chb & ~1) * 8, rank * 32 + 28);
        if (gidx != 0) wait_flag(g_flag_h + (hp >> 2), epoch);
      }
      __syncwarp();
      {
        uint4 hk0 = make_uint4(0, 0, 0, 0), hk1 = hk0, hv0 = hk0, hv1 = hk0;
        if (gidx != 0) {
          const uint4* src = g_halo + cta * 128 + lane;
          hk0 = __ldcg(src); hk1 = __ldcg(src + 32); hv0 = __ldcg(src + 64); hv1 = __ldcg(src + 96);
        }
        if (lane == 0) {
          mbar_wait(bars + 8 * (BAR_EMPTYB + 3), 1);
          bulk_load(sb + OFF_T, tab, T_TW, bars + 8 * BAR_T);
        }
        __syncwarp();
        PROF2(18);
        sts128(sb + OFF_L0 + 1024 + lane * 16, hk0.x, hk0.y, hk0.z, hk0.w);
        sts128(sb + OFF_L0 + 1536 + lane * 16, hk1.x, hk1.y, hk1.z, hk1.w);
        stsm4(sb + OFF_L0 + lr * 128 + ((lm ^ lr) << 4), hv0.x, hv0.y, hv0.z, hv0.w);
        stsm4(sb + OFF_L0 + lr * 128 + (((4 + lm) ^ lr) << 4), hv1.x, hv1.y, hv1.z, hv1.w);
        __syncwarp();
        if (lane == 0) {
          mbar_arrive(bars + 8 * BAR_STG);
          mbar_wait(bars + 8 * (BAR_EMPTYB + 4), 1);
          bulk_load(sb + OFF_T + T_TW, tab + T_TW, T_A1 - T_TW, bars + 8 * BAR_T);
          if (MODE == 0) {
            mbar_expect_tx(bars + 8 * BAR_FULL2, STG2);
            tma_load_3d(sb + g2_b(0), &tmWo, bars + 8 * BAR_FULL2, 0, g2_k(hp, 0) * 64, cb2 * 2);
            tma_load_3d(sb + g2_b(1), &tmWo, bars + 8 * (BAR_FULL2 + 1), 0, g2_k(hp, 1) * 64, cb2 * 2);
          }
          mbar_wait(bars + 8 * BAR_EMPTYB, 0);
#pragma unroll 1
          for (int i = 0; i < 6; i++) tma_load_5d(sb + OFF_Q + i * 4096, &tmQ, bars + 8 * BAR_Q, (chb & ~1) * 8, rank * 32 + i * 4);
        }
        __syncwarp();
      }
      }
      if (MODE != 1) {
        auto korder = [&](int i) { return MODE == 2 ? i : g2_k(hp, i); };
        const __nv_bfloat16* osrc = g_o + (size_t)(rb2 >> 1) * 16 * 16384 + ((rb2 & 1) * 2 + rank) * 4096;
        const uint32_t* flag = g_flag_o + (rb2 >> 1) * 32 + korder(lane & 15) * 2 + (rb2 & 1);
        uint32_t ready = MODE == 0 ? 0u : ~0u, pv = 0;
        auto look = [&]() {
          ready |= __ballot_sync(0xffffffffu, pv == epoch);
          asm volatile("fence.acquire.gpu;\n" ::: "memory");
          fence_async_all();
        };
        if (MODE == 0) mbar_wait_idle(bars + 8 * BAR_REL, 0);
#pragma unroll
        for (int i = MODE == 0 ? 2 : 0; i < 16; i++) {
          const int kb = korder(i), s = i % NS2, ph = (i / NS2) & 1;
          const uint32_t fb = bars + 8 * (BAR_FULL2 + s);
          if (!((ready >> i) & 1)) {
            int n = 0;
            do {
              ready |= __ballot_sync(0xffffffffu, ld_acquire(flag) == epoch);
            } while (!((ready >> i) & 1) && ++n < SPIN_LIMIT);
            fence_async_all();
          }
          if (i == 2) PROF(21);
          mbar_wait(bars + 8 * (BAR_EMPTY2 + s), ph);
          if (elect_one()) {
            mbar_expect_tx(fb, STG2);
            asm volatile(
                "cp.async.bulk.shared::cluster.global.mbarrier::complete_tx::bytes.multicast::cluster [%0], [%1], %2, [%3], %4;\n"
                ::"r"(sb + g2_a(s, rb2 & 1) + rank * 8192), "l"(osrc + kb * 16384), "r"(8192), "r"(fb), "h"((uint16_t)3) : "memory");
            if (MODE != 0 || i >= 4) tma_load_3d(sb + g2_b(s), &tmWo, fb, 0, kb * 64, cb2 * 2);
          }
          if (MODE == 0 && i == LA0) pv = ld_relaxed(flag);
          if (MODE == 0 && i == LA1) look();
          if (i == 3) PROF(37);

        }
      }
      __syncwarp();
    } else if (MODE != 2) {
      {
        const int g = lane >> 2, t = lane & 3;
        uint32_t w[2][4];
#pragma unroll
        for (int h = 0; h < 2; h++) {
          const uint2 x = __ldg(reinterpret_cast<const uint2*>(p.shift_k + ((chb & ~1) * 8 + h * 8 + g) * 4));
          w[h][0] = __byte_perm(x.x, x.x, 0x1010);
          w[h][1] = __byte_perm(x.x, x.x, 0x3232);
          w[h][2] = __byte_perm(x.y, x.y, 0x1010);
          w[h][3] = __byte_perm(x.y, x.y, 0x3232);
        }
        auto swz = [](int r) { return (((r & 29) | ((r ^ (r >> 2)) & 2)) << 5) | (r & 16); };
        const uint32_t kring = sb + OFF_H + (hw - 1) * 8192, vring = kring + 4096;
        const int s0 = rank * 32 + (hw - 1) * 11, s1 = hw == 3 ? rank * 32 + 32 : s0 + 11;
        const size_t goff = (size_t)(lane >> 1) * DM + (chb & ~1) * 8 + (lane & 1) * 8;
        const __nv_bfloat16* kg = p.k + goff;
        const __nv_bfloat16* vg = p.v + goff;
        const uint32_t d0 = swz(lane >> 1) ^ ((lane & 1) << 4), d1 = swz(16 + (lane >> 1)) ^ ((lane & 1) << 4);
        auto issue = [&](int st) {
          const uint32_t so = (st & 3) << 10;
          cp_async16(kring + so + d0, kg + (size_t)st * 32 * DM, 16);
          cp_async16(kring + so + d1, kg + (size_t)(st * 32 + 16) * DM, 16);
          cp_async16(vring + so + d0, vg + (size_t)st * 32 * DM, 16);
          cp_async16(vring + so + d1, vg + (size_t)(st * 32 + 16) * DM, 16);
        };
        const int xa = 8 * (lr >> 1) + 2 * lm + (lr & 1), xb = 8 * (lr >> 1) - 4 + 2 * (lm & 1) + (lr & 1);
        const uint32_t la = swz(xa), lb = swz(xb & 31);
        const int backb = xb < 0 ? 1 : 0;
        const uint32_t ud[2] = {mapa(sb + OFF_U + g * 4096 + t * 16, 0), mapa(sb + OFF_U + g * 4096 + t * 16, 1)};
        const uint32_t ub[2] = {mapa(bars + 8 * BAR_U, 0), mapa(bars + 8 * BAR_U, 1)};
        if (lane == 0) mbar_wait(bars + 8 * (BAR_FULLB + NS1B - 1), 0);
        __syncwarp();
        if (lane >= 24) cp_async16(kring + (((s0 - 1) & 3) << 10) + d1, s0 > 0 ? kg + (size_t)(s0 * 32 - 16) * DM : kg, s0 > 0 ? 16 : 0);
        issue(s0);
        asm volatile("cp.async.commit_group;\n" ::: "memory");
        issue(s0 + 1);
        asm volatile("cp.async.commit_group;\n" ::: "memory");
#pragma unroll 1
        for (int st = s0; st < s1; st++) {
          if (st + 2 < s1) issue(st + 2);
          if (hw == 1 && st - s0 < 8) prefetch_l2(p.ssm_k + (size_t)(chb * 8 + st - s0) * SEQ + lane * 64);
          if (hw == 2 && st == s0 + 4 && lane < 2) prefetch_l2(g_tab + (chb * 2 + lane) * 32);
          const uint32_t uo = (st ^ ((g ^ (st >> 2)) & 1)) * 64;
          asm volatile("cp.async.commit_group;\n" ::: "memory");
          asm volatile("cp.async.wait_group 2;\n" ::: "memory");
          __syncwarp();
#pragma unroll
          for (int h = 0; h < 2; h++) {
            uint32_t e[6], vv[4], e4[4];
            ldsm4t(e4, kring + ((st & 3) << 10) + (la ^ (h << 4)));
            ldsm2t(e[0], e[1], kring + (((st - backb) & 3) << 10) + (lb ^ (h << 4)));
            ldsm4t(vv, vring + ((st & 3) << 10) + (la ^ (h << 4)));
            e[2] = e4[0]; e[3] = e4[1]; e[4] = e4[2]; e[5] = e4[3];
            uint32_t o[5];
#pragma unroll
            for (int i = 0; i < 5; i++) o[i] = __byte_perm(e[i], e[i + 1], 0x5432);
#pragma unroll
            for (int i = 0; i < 4; i++) {
              uint32_t a = bmul2(o[i], w[h][3]);
              a = bfma2(e[i + 1], w[h][2], a);
              a = bfma2(o[i + 1], w[h][1], a);
              a = bfma2(e[i + 2], w[h][0], a);
              vv[i] = bmul2(a, vv[i]);
            }
            st_async128(ud[h] + uo, ub[h], vv[0], vv[1], vv[2], vv[3]);
          }
          __syncwarp();
        }
        PROF(16);
      }
      {
        const int rw = (lane >> 3) + (lane & 4), ck = lane & 3;
        const uint32_t so = rw * 64 + ck * 16, dof = rw * 128 + ((ck ^ rw) << 4);
        const uint8_t* hsrc = reinterpret_cast<const uint8_t*>(p.ssm_k + (size_t)chb * 8 * SEQ) + so;
        const float dv = lane < 8 ? __bfloat162float(p.ssm_D[chb * 8 + lane]) : 0.f;
        uint32_t x[32];
        auto load = [&](const uint8_t* src, int i) {
          asm volatile("ld.v4.u32 {%0,%1,%2,%3}, [%4];\n" : "=r"(x[4 * i]), "=r"(x[4 * i + 1]), "=r"(x[4 * i + 2]), "=r"(x[4 * i + 3])
                       : "l"(src + i * 512) : "memory");
        };
#pragma unroll
        for (int i = 0; i < 8; i++) load(hsrc + (hw - 1) * 4096, i);
        nb_sync(NB_HELP3, 96);
        mbar_wait(bars + 8 * BAR_U, 0);
        int eh = 0;
#pragma unroll 1
        for (int n = 2 * (hw - 1); n < 16; n += (n & 1) ? 5 : 1) {
          const int c = n >> 1;
          const uint8_t* nsrc = (n & 1) ? hsrc + (c < 5 ? c + 3 : c) * 4096
                                        : smem + OFF_U + c * 4096 + (so ^ (((c ^ (lane >> 2)) & 1) << 6));
          const uint32_t dst = sb + ((n & 1) ? OFF_U : OFF_H) + c * 4096 + dof;
          const float dc = __shfl_sync(0xffffffffu, dv, c);
          const float h0 = bf_lo(x[0]) + ((lane | (n & 1)) == 0 ? dc : 0.f), h1 = bf_hi(x[0]);
          x[0] = pack_bf16(h0, h1);
          uint32_t m[2] = {x[0], x[1]};
#pragma unroll
          for (int i = 2; i < 32; i++) asm("max.xorsign.abs.bf16x2 %0, %0, %1;\n" : "+r"(m[i & 1]) : "r"(x[i]));
          asm("max.xorsign.abs.bf16x2 %0, %0, %1;\n" : "+r"(m[0]) : "r"(m[1]));
          const uint32_t e = max(__reduce_max_sync(0xffffffffu, max((m[0] >> 7) & 255u, (m[0] >> 23) & 255u)), 5u);
          const uint32_t sc = (259u - e) * 0x00800080u;
#pragma unroll
          for (int i = 0; i < 8; i++) {
            uint32_t o[4];
#pragma unroll
            for (int j = 0; j < 4; j++) {
              const uint32_t v = bmul2(x[4 * i + j], sc);
              asm("cvt.rn.f16x2.f32 %0, %1, %2;\n" : "=r"(o[j]) : "f"(bf_hi(v)), "f"(i + j == 0 ? h0 * bf_hi(sc) : bf_lo(v)));
            }
            sts128((dst + (i & 3) * 1024) ^ ((i >> 2) << 6), o[0], o[1], o[2], o[3]);
            load(nsrc, i);
          }
          if (n & 1) {
            const int f = min(max((int)e + eh - 129, 0), 254);
            if (lane < 2)
              asm volatile("st.async.weak.shared::cluster.mbarrier::complete_tx::bytes.b32 [%0], %2, [%1];\n"
                           ::"r"(mapa(sb + OFF_SC + rank * 32 + c * 4, lane)), "r"(mapa(bars + 8 * BAR_LAND, lane)), "r"(f << 7) : "memory");
          }
          eh = e;
        }
        fence_async_smem();
        __syncwarp();
        if (lane == 0) mbar_arrive(bars + 8 * BAR_UH);
        PROF(32);
      }
      if (hw < 3) {
        const uint32_t rb = mapa(bars, lane & 1);
        const uint32_t epoch = ld_relaxed(g_flag_o + 2 * cta + hw - 1) + 1;
        const bool own = hw - 1 == (rb2 & 1);
        nb_sync(NB_OREADY + hw - 1, 160);
        if (lane == 0) {
          asm volatile("cp.async.bulk.global.shared::cta.bulk_group [%0], [%1], %2;\n" ::"l"(g_o + (size_t)cta * 16384 + (hw - 1) * 8192),
                       "r"(sb + OFF_OP + (hw - 1) * 16384), "r"(16384) : "memory");
          bulk_commit();
        }
        if (lane < 2) {
          mbar_arrive_cluster(rb + 8 * (BAR_EMPTY2 + 2));
          mbar_arrive_cluster(rb + 8 * (BAR_EMPTY2 + 3));
        }
        if (lane == 0) {
          bulk_wait0();
          if (own) mbar_expect_tx(bars + 8 * (BAR_FULL2 + 1), 16384);
          mbar_arrive_cluster(mapa(bars, own ? rank : rank ^ 1) + 8 * BAR_X);
          st_release(g_flag_o + 2 * cta + hw - 1, epoch);
          mbar_arrive(bars + 8 * BAR_REL);
        }
        __syncwarp();
        PROF(own ? 17 : 19);
      } else {
        if (MODE == 0) {
          mbar_wait_idle(bars + 8 * BAR_X, 0);
          if (elect_one())
            asm volatile("cp.async.bulk.shared::cluster.shared::cta.mbarrier::complete_tx::bytes [%0], [%1], %2, [%3];\n"
                         ::"r"(mapa(sb + g2_a(0, rb2 & 1), rank ^ 1)), "r"(sb + g2_a(1, rb2 & 1)), "r"(16384),
                         "r"(mapa(bars + 8 * BAR_FULL2, rank ^ 1)) : "memory");
        }
        if (MODE == 0) {
          mbar_wait_idle(bars + 8 * BAR_DEAD, 0);
          if (elect_one()) {
            tma_load_3d(sb + g2_b(2), &tmWo, bars + 8 * (BAR_FULL2 + 2), 0, g2_k(hp, 2) * 64, cb2 * 2);
            tma_load_3d(sb + g2_b(3), &tmWo, bars + 8 * (BAR_FULL2 + 3), 0, g2_k(hp, 3) * 64, cb2 * 2);
          }
        }
        __syncwarp();
      }
      {
        const int c8 = (4 * (lr >> 1) + 2 * (lm & 1) + (lr & 1)) & 7;
        const bool own = (lr >> 2) == rank;
        const uint32_t ya = sb + (own ? y_slot(c8 & 1, c8 >> 1) : OFF_LAND + c8 * 2048);
        const uint32_t yx = ((lm >> 1) ^ lr) << 4;
        const int row = (lane >> 4) * 8 + ((lane >> 3) & 1) * 16 + ((lane >> 2) & 1);
        uint2* og = reinterpret_cast<uint2*>(p.out + (size_t)(rank * 1024 + row) * (2 * DM) + (chb & ~1) * 8 + (lane & 3) * 4);
        const uint32_t qa = sb + OFF_Q + (lane >> 4) * 512 + (lane & 15) * 8;
        mbar_wait(bars + 8 * BAR_Q, 0);
        mbar_wait_idle(bars + 8 * BAR_LAND, 0);
        PROF(33);
        const uint32_t t0 = clock();
        const uint4 s4 = lds128(sb + OFF_SC + (lane & 3) * 16);
        const uint32_t sc[2] = {s4.x | (s4.y << 16), s4.z | (s4.w << 16)};
        auto fin = [&](uint32_t q2, uint32_t y2, uint32_t s2) {
          float lo, hi;
          asm("{\n.reg .b16 l, h;\nmov.b32 {l, h}, %2;\ncvt.f32.f16 %0, l;\ncvt.f32.f16 %1, h;\n}\n" : "=f"(lo), "=f"(hi) : "r"(y2));
          return bmul2(q2, bmul2(pack_bf16(lo, hi), s2));
        };
#pragma unroll 1
        for (int j = hw - 1; j < 16; j += 3) {
          uint32_t y[4][4];
          uint2 q[8];
          while ((uint32_t)clock() - t0 < j * PACE) __nanosleep(40);
          const uint32_t qj = qa + j * 2048;
#pragma unroll
          for (int i = 0; i < 4; i++) ldsm4t(y[i], ya + j * 128 + (yx ^ (i << 5)));
#pragma unroll
          for (int i = 0; i < 8; i++) q[i] = lds64(qj + (i >> 2) * 1024 + (i & 3) * 128);
#pragma unroll
          for (int i = 0; i < 8; i++) {
            og[(size_t)(j * 64 + (i >> 2) * 32 + (i & 3) * 2) * (2 * DM / 4)] =
                make_uint2(fin(q[i].x, y[i >> 1][2 * (i & 1)], sc[0]), fin(q[i].y, y[i >> 1][2 * (i & 1) + 1], sc[1]));
            if (i < 7) asm volatile("nanosleep.u32 %0;\n" ::"r"(FINE) : "memory");
          }
        }
      }
      PROF(22);
    }
    cluster_sync_all();
  } else {
    asm volatile("setmaxnreg.inc.sync.aligned.u32 %0;\n" :: "n"(REG_MATH));
    if (warp == 0) PROF2(26);
    const int wg = warp >> 2;
    const int wtid = tid & 127;
    const bool signaller = (wtid == 0) || (wtid == 32);
    const uint32_t rbars = mapa(bars, wtid >> 5 & 1);

    if (halo_cta) {
      const uint32_t epoch = ld_relaxed(g_flag_h + blockIdx.x) + 1;
      float acc0[64], acc1[64];
      int s = 0, ph = 0;
#pragma unroll 1
      for (int kb = 0; kb < 16; kb++) {
        mbar_wait(bars + 8 * (BAR_FULLB + s), ph);
        const uint32_t st = sb + s * STGH;
        const uint64_t da = mkdesc(st, 16, 1024, 1);
        const uint64_t db = mkdesc(st + 8192 + wg * 32768, 8192, 1024, 1);
        wg_fence();
#pragma unroll
        for (int kk = 0; kk < 4; kk++) {
          wgmma_n128(acc0, da + 2 * kk, db + 128 * kk, kb + kk);
          wgmma_n128(acc1, da + 2 * kk, db + 1024 + 128 * kk, kb + kk);
        }
        wg_commit();
        wg_wait<0>();
        if (wtid == 0) mbar_arrive(bars + 8 * (BAR_EMPTYB + s));
        if (++s == 3) { s = 0; ph ^= 1; }
      }
      fence_regs(acc0);
      fence_regs(acc1);
      if ((warp & 3) != 3) {
#pragma unroll
        for (int hh = 0; hh < 2; hh++) {
          uint4* dst = g_halo + ((hh * 4 + (warp & 3) + 1) * 16 + blockIdx.x * 4) * 128 + wg * 64 + lane;
#pragma unroll
          for (int j = 0; j < 4; j++) {
            const int o = 16 * j + 2 * hh;
            dst[(j >> 1) * 128 + (j & 1) * 32] =
                make_uint4(pack_bf16(acc0[o], acc0[o + 1]), pack_bf16(acc0[o + 4], acc0[o + 5]),
                           pack_bf16(acc0[o + 8], acc0[o + 9]), pack_bf16(acc0[o + 12], acc0[o + 13]));
            dst[(2 + (j >> 1)) * 128 + (j & 1) * 32] =
                make_uint4(pack_bf16(acc1[o], acc1[o + 1]), pack_bf16(acc1[o + 4], acc1[o + 5]),
                           pack_bf16(acc1[o + 8], acc1[o + 9]), pack_bf16(acc1[o + 12], acc1[o + 13]));
          }
        }
      }
      nb_sync(NB_G1DONE, 256);
      if (tid == 0) st_release(g_flag_h + blockIdx.x, epoch);
      PROF(36);
      cluster_sync_all();
      return;
    }

    float acc[64];
    auto g2_step = [&](int s, int kb) {
      const uint64_t da = mkdesc(sb + g2_a(s, rb2 & 1) + wg * 8192, 16, 1024, 1);
      const uint64_t db = mkdesc(sb + g2_b(s), 8192, 1024, 1);
      wg_fence();
      wgmma_n128(acc, da, db, kb);
      wgmma_n128(acc, da + 2, db + 128, 1);
      wgmma_n128(acc, da + 4, db + 256, 1);
      wgmma_n128(acc, da + 6, db + 384, 1);
      wg_commit();
    };

    if (MODE != 2) {
    uint32_t a1[2][4], tw[16], d1[32];
    const uint32_t tb = sb + OFF_T + wtid * 16;
    const uint64_t dx = mkdesc(sb + OFF_U + wg * 4096, OFF_H - OFF_U, 1024, 1);
    auto s1 = [&](int it) {
      hmma_n128t<0>(d1, a1[0], dx + it * 512);
      hmma_n128t<1>(d1, a1[1], dx + it * 512 + 128);
      wg_commit();
    };
    auto ldtw = [&](int i) {
      const uint4 v = lds128(tb + T_TW + i * 2048);
      tw[4 * i] = v.x; tw[4 * i + 1] = v.y; tw[4 * i + 2] = v.z; tw[4 * i + 3] = v.w;
    };
    {
      float acc0[96], acc1[96];
      int sa = 0, pha = 0, sbb = 0, phb = 0;
      asm volatile("cp.async.wait_group 0;\n" ::: "memory");
      fence_async_smem();
      nb_sync(NB_FIRST, 256);
      if (tid == 0) {
        mbar_arrive(bars + 8 * BAR_FULLA);
        mbar_arrive(bars + 8 * BAR_FULLB);
      }
      PROF(0 + wg);
#pragma unroll 1
      for (int kb = 0; kb < 30; kb++) {
        if (!(kb & 1)) mbar_wait(bars + 8 * (BAR_FULLA + sa), pha);
        mbar_wait(bars + 8 * (BAR_FULLB + sbb), phb);
        if (kb == 0) PROF2(0 + wg);
        if (kb == 4 && wg == 0) PROF2(28);
        if (kb == 8 && wg == 0) PROF2(29);
        if (kb == 16 && wg == 0) PROF2(30);
        const uint64_t da = mkdesc(sb + sa * STG1A + wg * 16384 + (kb & 1) * 64, 16, 1024, 1);
        const uint64_t db = mkdesc(sb + OFF_1B + sbb * STG1B, 4096, 1024, 1);
        wg_fence();
        wgmma_n192(acc0, da, db, kb);
        wgmma_n192(acc1, da + 512, db, kb);
        wgmma_n192(acc0, da + 2, db + 128, 1);
        wgmma_n192(acc1, da + 514, db + 128, 1);
        wg_commit();
        wg_wait<1>();
        if (kb > 0) {
          if (wtid == 64) mbar_arrive(bars + 8 * (BAR_EMPTYB + (sbb == 0 ? NS1B - 1 : sbb - 1)));
          if (!(kb & 1) && signaller) mbar_arrive_cluster(rbars + 8 * (BAR_EMPTYA + (sa == 0 ? NS1A - 1 : sa - 1)));
        }
        if (++sbb == NS1B) { sbb = 0; phb ^= 1; }
        if ((kb & 1) && ++sa == NS1A) { sa = 0; pha ^= 1; }
      }
      const int blk0 = wg * 8 + (warp & 3);
      const int lr = lane & 7, lm = lane >> 3;
      const bool le0 = 2 * (lane & 3) <= (lane >> 2), le1 = 2 * (lane & 3) + 1 <= (lane >> 2);
      const uint32_t maskLE = (le0 ? 0x0000FFFFu : 0u) | (le1 ? 0xFFFF0000u : 0u);
      uint32_t k0[2][2][4], k1[2][2][4], qa[2][2][8];
      float l[2][2][4];
      {
        static_assert(15 % NS1A == 0 && 30 % NS1B == 0, "slots of the last k blocks");
        mbar_wait(bars + 8 * BAR_FULLA, 1);
        mbar_wait(bars + 8 * BAR_FULLB, 0);
        mbar_wait(bars + 8 * (BAR_FULLB + 1), 0);
        mbar_wait(bars + 8 * (BAR_EMPTYB + 2), 1);
        const uint64_t da = mkdesc(sb + wg * 16384, 16, 1024, 1);
        const uint64_t db = mkdesc(sb + OFF_1B, 4096, 1024, 1);
        wg_fence();
#pragma unroll
        for (int i = 0; i < 4; i++) wgmma_n192(acc0, da + 2 * i, db + (i >> 1) * (STG1B >> 4) + (i & 1) * 128, 1);
        wg_commit();
        wg_wait<1>();
        if (wtid == 64) mbar_arrive(bars + 8 * (BAR_EMPTYB + NS1B - 1));
#pragma unroll
        for (int i = 0; i < 2; i++) wgmma_n192(acc1, da + 512 + 2 * i, db + (i >> 1) * (STG1B >> 4) + (i & 1) * 128, 1);
        wg_commit();
        wg_wait<1>();
        fence_regs(acc0);
        attn_stage(sb, blk0, lane, acc0, k1[0]);
#pragma unroll
        for (int i = 2; i < 4; i++) wgmma_n192(acc1, da + 512 + 2 * i, db + (i >> 1) * (STG1B >> 4) + (i & 1) * 128, 1);
        wg_commit();
        attn_pack(acc0, qa[0], k0[0]);
        wg_wait<0>();
        fence_regs(acc1);
      }
      if (wtid == 64) mbar_arrive(bars + 8 * BAR_EMPTYB);
      PROF(2 + wg);
      attn_stage(sb, blk0 + 4, lane, acc1, k1[1]);
      __syncwarp();
      if (lane == 0) mbar_arrive(bars + 8 * BAR_STG);
      mbar_wait(bars + 8 * BAR_U, 0);
      attn_pack(acc1, qa[1], k0[1]);
      attn_own(k0[0], k1[0], le0, le1, qa[0], l[0]);
      attn_own(k0[1], k1[1], le0, le1, qa[1], l[1]);
      const uint32_t cho[2] = {(uint32_t)(((lm & 1) ^ lr) << 4), (uint32_t)(((2 + (lm & 1)) ^ lr) << 4)};
      const uint32_t obase = sb + OFF_OP + (blk0 * 16 + lr) * 128;
      mbar_wait(bars + 8 * BAR_STG, 0);
      {
        uint32_t km[4][4], va[8][4], vb[8][4], pp[8];
        float x[8][2];
#pragma unroll
        for (int n = 0; n < 4; n++) {
          const int blk = blk0 + 4 * (n >> 1);
          to_arr(km[n], lds128(sb + (blk == 0 ? OFF_L0 + 1024 : OFF_OP + blk * 2048) + (n & 1) * 512 + lane * 16));
        }
#pragma unroll
        for (int n = 0; n < 8; n++) {
          const int vr = (blk0 + 4 * ((n >> 1) & 1)) * 16 - 8 + 8 * (n >> 2) + 8 * (lm >> 1);
          const uint32_t vrow = sb + (vr < 0 ? OFF_L0 : OFF_VP + vr * 128) + lr * 128;
          ldsm4t(va[n], vrow + (cho[0] ^ ((n & 1) << 6)));
          ldsm4t(vb[n], vrow + (cho[1] ^ ((n & 1) << 6)));
        }
        const bool first = blk0 == 0 && gidx == 0;
#pragma unroll
        for (int n = 0; n < 4; n++) {
          const uint32_t(&q)[8] = qa[n >> 1][n & 1];
          float sm[4];
          mma16816_z(sm, q[0], q[1], q[2], q[3], km[n][0], km[n][1]);
          mma16816(sm, q[4], q[5], q[6], q[7], km[n][2], km[n][3]);
          if (n < 2 && first) sm[0] = sm[1] = -1e9f / 0.17677669529663687f;
          x[n][0] = le0 ? l[n >> 1][n & 1][0] : sm[0];
          x[n][1] = le1 ? l[n >> 1][n & 1][1] : sm[1];
          x[4 + n][0] = l[n >> 1][n & 1][2];
          x[4 + n][1] = l[n >> 1][n & 1][3];
        }
        quad_softmax<8>(x, pp);
#pragma unroll
        for (int n = 7; n >= 0; n--)
          attn_pv(obase + ((n >> 1) & 1) * 8192 + (n >> 2) * 1024 + (((4 * (n & 1) + lm) ^ lr) << 4), va[n], vb[n], pp[n],
                  maskLE);
      }
      fence_async_smem();
      nb_arrive(NB_OREADY + wg, 160);
    }

    {
      const int w = warp & 3;
      uint32_t a4[8][4];
      uint32_t d4[8];
      PROF(34 + wg);
      const uint64_t dz = mkdesc(sb + OFF_U + wg * 4096, 512, 128, 0);
      const uint64_t db2 = mkdesc(sb + OFF_T + T_B2, 128, 256, 0);
      mbar_wait(bars + 8 * BAR_T, 0);
      mbar_wait(bars + 8 * BAR_UH, 0);
      to_arr(a1[0], lds128(tb + T_A1));
      to_arr(a1[1], lds128(tb + T_A1 + 2048));
      wg_fence();
      s1(0);
      ldtw(0);
      ldtw(1);
      const uint32_t za = sb + (w < 2 ? OFF_U : OFF_H) + wg * 4096 + (w & 1) * 2048 + lane * 16;
      const uint32_t yl = (wtid ^ (4 * rank + wg)) * 16;
      const uint32_t yown = mapa(sb, rank) + yl, yrem = mapa(sb + OFF_LAND + wg * 2048, rank ^ 1) + yl;
      const uint32_t yb[2] = {mapa(bars + 8 * BAR_LAND, 0), mapa(bars + 8 * BAR_LAND, 1)};
      wg_wait<0>();
      fence_regs(d1);
      nb_sync(NB_WG + wg, 128);
      auto s4 = [&](int it) {
        wg_fence();
#pragma unroll
        for (int ks = 0; ks < 8; ks++) {
          const uint64_t d = dz + (it & 1) * 512 + (ks & 3) * 64 + (ks >> 2) * ((OFF_H - OFF_U) >> 4);
          if (ks == 0) hmma_n32<0, 1>(d4, a4[ks], d);
          else hmma_n32<1, 1>(d4, a4[ks], d);
        }
        wg_commit();
      };
      auto e4 = [&](int it) {
        fence_regs(d4);
        const uint32_t o = (yown + y_slot(wg, it)) ^ ((it >> 1) << 5), m = (yrem + it * 4096) ^ ((it >> 1) << 5);
        if (it == 0) mbar_wait(bars + 8 * BAR_LFREE, 0);
        if (it == 3) mbar_wait(bars + 8 * (BAR_DEAD + 1), 0);
        st_async128(rank ? m : o, yb[0], d4[0], d4[1], d4[2], d4[3]);
        st_async128(rank ? o : m, yb[1], d4[4], d4[5], d4[6], d4[7]);
      };
      uint32_t a2[2][2][2][4], a3[2][2][4], d2[2][2][8], d3[2][8];
      auto s2a = [&]() {
        wg_fence();
#pragma unroll
        for (int c = 0; c < 4; c++) hmma_n32<0, 0>(d2[c & 1][c >> 1], a2[0][c & 1][c >> 1], db2 + (c >> 1) * 128);
      };
      auto s2b = [&]() {
        wg_fence();
#pragma unroll
        for (int c = 0; c < 4; c++) {
          hmma_n32<1, 0>(d2[c & 1][c >> 1], a2[1][c & 1][c >> 1], db2 + (c >> 1) * 128 + 64);
          if (c & 1) wg_commit();
        }
      };
      auto done = [&](int it) {
        if (it == 0) {
          if (signaller) mbar_arrive_cluster(rbars + 8 * BAR_LFREE);
        } else if (it >= 2 && wtid == 64) {
          mbar_arrive(bars + 8 * (BAR_DEAD + it - 2));
        }
        if (w == 0) PROF3(40 + 4 * wg + it);
      };
      fft_e1<0>(d1, tw, a2[0]);
      s2a();
      fft_e1<1>(d1, tw, a2[1]);
      s2b();
      s1(1);
      ldtw(2);
      ldtw(3);
#pragma unroll
      for (int i = 0; i < 8; i++) to_arr(a4[i], lds128(tb + T_A4 + i * 2048));
#pragma unroll
      for (int it = 0; it < 4; it++) {
        if (it == 0 || it == 3) wg_wait<2>(); else wg_wait<3>();
        fence_regs(d2[0][0]);
        fence_regs(d2[1][0]);
        fft_e2<0, 0>(d2[0][0], d2[1][0], a3[0]);
        fft_e2<0, 1>(d2[0][0], d2[1][0], a3[1]);
        if (it == 0 || it == 3) wg_wait<1>(); else wg_wait<2>();
        fence_regs(d2[0][1]);
        fence_regs(d2[1][1]);
        fft_e2<1, 0>(d2[0][1], d2[1][1], a3[0]);
        fft_e2<1, 1>(d2[0][1], d2[1][1], a3[1]);
        wg_fence();
        hmma_n32<0, 0>(d3[0], a3[0][0], db2);
        hmma_n32<0, 0>(d3[1], a3[0][1], db2);
        hmma_n32<1, 0>(d3[0], a3[1][0], db2 + 64);
        hmma_n32<1, 0>(d3[1], a3[1][1], db2 + 64);
        wg_commit();
        wg_wait<1>();
        if (it > 0) e4(it - 1);
        if (it < 3) {
          fence_regs(d1);
          fft_e1<0>(d1, tw, a2[0]);
        }
        wg_wait<0>();
        fence_regs(d3[0]);
        fence_regs(d3[1]);
        if (it < 3) s2a();
        fft_e3(d3, tw, za + (it & 1) * 8192);
        if (it < 3) {
          fft_e1<1>(d1, tw, a2[1]);
          s2b();
        }
        fence_async_smem();
        nb_sync(NB_WG + wg, 128);
        done(it);
        s4(it);
        if (it < 2) s1(it + 2);
      }
      if (PEEL && MODE == 0) {
        mbar_wait(bars + 8 * BAR_FULL2, 0);
        g2_step(0, 0);
        wg_wait<1>();
      } else {
        wg_wait<0>();
      }
      if (signaller) mbar_arrive_cluster(rbars + 8 * (BAR_EMPTY2 + 4));
      e4(3);
      if (PEEL && MODE == 0) {
        wg_wait<0>();
        if (signaller) mbar_arrive_cluster(rbars + 8 * BAR_EMPTY2);
      }
      PROF(6 + wg);
    }
    }

    if (MODE != 1) {
      int s = PEEL && MODE == 0, ph = 0;
#pragma unroll 1
      for (int kb = s; kb < STAG; kb++) {
        mbar_wait(bars + 8 * (BAR_FULL2 + s), ph);
        if (kb == 1) PROF(8 + wg);
        if (warp == 4) PROF2(40 + kb);
        g2_step(s, kb);
        wg_wait<0>();
        if (kb < 16 - NS2 && signaller) mbar_arrive_cluster(rbars + 8 * (BAR_EMPTY2 + s));
        if (++s == NS2) { s = 0; ph ^= 1; }
      }
      if (STAG < 16) {
        if (wg == LAST) nb_sync(NB_LEAD, 256);
#pragma unroll
        for (int kb = STAG; kb < 16; kb++) {
          mbar_wait(bars + 8 * (BAR_FULL2 + kb % NS2), (kb / NS2) & 1);
          g2_step(kb % NS2, 1);
        }
        if (wg != LAST) nb_arrive(NB_LEAD, 256);
      }
      wg_wait<0>();
      fence_regs(acc);
      PROF(10 + wg);
      const int lr = lane & 7, lm = lane >> 3;
      const uint32_t wbase = sb + warp * 2048;
      const uint32_t base = wbase + (lr + 8 * (lm & 1)) * 128;
#pragma unroll
      for (int j = 0; j < 16; j += 2) {
        const uint32_t a = base + (j >> 3) * 16384 + ((((j & 7) + (lm >> 1)) ^ lr) << 4);
        stsm4(a, pack_bf16(acc[4 * j], acc[4 * j + 1]), pack_bf16(acc[4 * j + 2], acc[4 * j + 3]),
              pack_bf16(acc[4 * j + 4], acc[4 * j + 5]), pack_bf16(acc[4 * j + 6], acc[4 * j + 7]));
      }
      __syncwarp();
      {
        const int rr = lane >> 4, ck = lane & 7, hf = (lane >> 3) & 1;
        uint4* og = reinterpret_cast<uint4*>(p.out + (size_t)(2 * ((rb2 & 7) * 128 + warp * 16 + rr) + (rb2 >> 3)) * (2 * DM) + DM + cb2 * 128 + hf * 64 + ck * 8);
        uint4 v[8];
#pragma unroll
        for (int i = 0; i < 8; i++) v[i] = lds128(wbase + hf * 16384 + (2 * i + rr) * 128 + ((ck ^ ((2 * i + rr) & 7)) << 4));
#pragma unroll
        for (int i = 0; i < 8; i++) og[(size_t)i * 4 * (2 * DM / 8)] = v[i];
      }
      PROF(12 + wg);
    }
    cluster_sync_all();
  }
}

typedef CUresult (*EncodeFn)(CUtensorMap*, CUtensorMapDataType, cuuint32_t, void*, const cuuint64_t*, const cuuint64_t*,
                             const cuuint32_t*, const cuuint32_t*, CUtensorMapInterleave, CUtensorMapSwizzle,
                             CUtensorMapL2promotion, CUtensorMapFloatOOBfill);

void make_map(EncodeFn enc, CUtensorMap* tm, const void* base, int rank, const cuuint64_t* dims, const cuuint64_t* strides,
              const cuuint32_t* box, CUtensorMapSwizzle swz) {
  cuuint32_t es[5] = {1, 1, 1, 1, 1};
  enc(tm, CU_TENSOR_MAP_DATA_TYPE_BFLOAT16, rank, const_cast<void*>(base), dims, strides, box, es,
      CU_TENSOR_MAP_INTERLEAVE_NONE, swz, CU_TENSOR_MAP_L2_PROMOTION_L2_256B, CU_TENSOR_MAP_FLOAT_OOB_FILL_NONE);
}

}

extern "C" void kernel_launch(void* const* d_in, const int* in_sizes, int n_in, void* d_out, int out_size) {
  static EncodeFn enc = nullptr;
  static bool coresident = true;
  if (!enc) {
    void* fn = nullptr;
    cudaDriverEntryPointQueryResult qr;
    cudaGetDriverEntryPoint("cuTensorMapEncodeTiled", &fn, cudaEnableDefault, &qr);
    enc = (EncodeFn)fn;
    cudaFuncSetAttribute(fused_kernel<0>, cudaFuncAttributeMaxDynamicSharedMemorySize, SMEM_BYTES);
    cudaFuncSetAttribute(fused_kernel<1>, cudaFuncAttributeMaxDynamicSharedMemorySize, SMEM_BYTES);
    cudaFuncSetAttribute(fused_kernel<2>, cudaFuncAttributeMaxDynamicSharedMemorySize, SMEM_BYTES);
    cudaLaunchConfig_t cfg = {};
    cfg.gridDim = dim3(NCTA);
    cfg.blockDim = dim3(NTHREADS);
    cfg.dynamicSmemBytes = SMEM_BYTES;
    cudaLaunchAttribute at;
    at.id = cudaLaunchAttributeClusterDimension;
    at.val.clusterDim.x = 2;
    at.val.clusterDim.y = 1;
    at.val.clusterDim.z = 1;
    cfg.attrs = &at;
    cfg.numAttrs = 1;
    int nclusters = 0;
    if (cudaOccupancyMaxActiveClusters(&nclusters, fused_kernel<0>, &cfg) == cudaSuccess) coresident = nclusters >= NCTA / 2;
    (void)cudaGetLastError();
  }
  CUtensorMap tmX, tmW, tmWo, tmQ, tmXh, tmWh;
  {
    cuuint64_t dims[3] = {1024, 2, 1024};
    cuuint64_t str[2] = {2048, 4096};
    cuuint32_t box[3] = {64, 1, 128};
    make_map(enc, &tmX, d_in[6], 3, dims, str, box, CU_TENSOR_MAP_SWIZZLE_128B);
  }
  {
    cuuint64_t dims[3] = {1024, 1024, 3};
    cuuint64_t str[2] = {6144, 2048};
    cuuint32_t box[3] = {64, 32, 3};
    make_map(enc, &tmW, d_in[7], 3, dims, str, box, CU_TENSOR_MAP_SWIZZLE_128B);
  }
  {
    cuuint64_t dims[3] = {64, 1024, 16};
    cuuint64_t str[2] = {2048, 128};
    cuuint32_t box[3] = {64, 64, 2};
    make_map(enc, &tmWo, d_in[8], 3, dims, str, box, CU_TENSOR_MAP_SWIZZLE_128B);
  }
  {
    cuuint64_t dims[5] = {1024, 2, 2, 8, 64};
    cuuint64_t str[4] = {2048, 16 * 2048, 2 * 2048, 32 * 2048};
    cuuint32_t box[5] = {16, 2, 2, 8, 4};
    make_map(enc, &tmQ, d_in[0], 5, dims, str, box, CU_TENSOR_MAP_SWIZZLE_NONE);
  }
  {
    cuuint64_t dims[4] = {1024, 256, 2, 4};
    cuuint64_t str[3] = {4096, 2048, 256 * 4096};
    cuuint32_t box[4] = {64, 8, 2, 4};
    make_map(enc, &tmXh, d_in[6], 4, dims, str, box, CU_TENSOR_MAP_SWIZZLE_128B);
  }
  {
    cuuint64_t dims[3] = {64, 1024, 48};
    cuuint64_t str[2] = {6144, 128};
    cuuint32_t box[3] = {64, 64, 4};
    make_map(enc, &tmWh, d_in[7], 3, dims, str, box, CU_TENSOR_MAP_SWIZZLE_128B);
  }
  Params p;
  p.q = (const __nv_bfloat16*)d_in[0];
  p.k = (const __nv_bfloat16*)d_in[1];
  p.v = (const __nv_bfloat16*)d_in[2];
  p.shift_k = (const __nv_bfloat16*)d_in[3];
  p.ssm_k = (const __nv_bfloat16*)d_in[4];
  p.ssm_D = (const __nv_bfloat16*)d_in[5];
  p.x = (const __nv_bfloat16*)d_in[6];
  p.w = (const __nv_bfloat16*)d_in[7];
  p.wo = (const __nv_bfloat16*)d_in[8];
  p.out = (__nv_bfloat16*)d_out;
  if (coresident) {
    fused_kernel<0><<<NCTA, NTHREADS, SMEM_BYTES>>>(p, tmX, tmW, tmWo, tmQ, tmXh, tmWh);
  } else {
    fused_kernel<0><<<4, NTHREADS, SMEM_BYTES>>>(p, tmX, tmW, tmWo, tmQ, tmXh, tmWh);
    fused_kernel<1><<<NCTA, NTHREADS, SMEM_BYTES>>>(p, tmX, tmW, tmWo, tmQ, tmXh, tmWh);
    fused_kernel<2><<<NCTA, NTHREADS, SMEM_BYTES>>>(p, tmX, tmW, tmWo, tmQ, tmXh, tmWh);
  }
}
```

```cpp
#include <cuda_runtime.h>
#include <cuda.h>
#include <cuda_bf16.h>
#include <stdint.h>

namespace {

constexpr int SEQ = 2048;
constexpr int DM = 1024;
constexpr int NCTA = 132;
constexpr int NTHREADS = 384;

constexpr int STG1A = 32768;
constexpr int NS1A = 3;
constexpr int STG1B = 12288;
constexpr int NS1B = 5;
constexpr int OFF_1B = NS1A * STG1A;
constexpr int STG2 = 32768;
constexpr int NS2 = 5;
constexpr int STGH = 73728;
constexpr int OFF_VP = 0;
constexpr int OFF_KH = 1 * STG2;
constexpr int OFF_OP = 2 * STG2;
constexpr int OFF_Q = 3 * STG2;
constexpr int T_A4 = 0, T_TW = 16384, T_B2 = 24576, T_A1 = 28672, T_END = 32768;
constexpr int OFF_U = 163840;
constexpr int OFF_H = OFF_U + 32768;
constexpr int OFF_T = OFF_U - T_END;
constexpr int OFF_LAND = 4 * STG2;
constexpr int OFF_BAR = OFF_H + 32768;
constexpr int OFF_SC = OFF_BAR + 512;
constexpr int OFF_L0 = -2048;
constexpr int SMEM_BYTES = 2048 + OFF_BAR + 1024;
static_assert(OFF_T + T_A1 == OFF_1B + NS1B * STG1B && OFF_T + T_TW == OFF_1B + 4 * STG1B && OFF_LAND == OFF_T + T_A4, "layout");
static_assert(3 * STGH <= OFF_BAR && SMEM_BYTES <= 232448, "smem");

constexpr int BAR_FULLA = 0;
constexpr int BAR_EMPTYA = 3;
constexpr int BAR_FULLB = 6;
constexpr int BAR_EMPTYB = 11;
constexpr int BAR_FULL2 = 16;
constexpr int BAR_EMPTY2 = 21;
constexpr int BAR_T = 26;
constexpr int BAR_UH = 27;
constexpr int BAR_LFREE = 28;
constexpr int BAR_LAND = 29;
constexpr int BAR_U = 30;
constexpr int BAR_Q = 31;
constexpr int BAR_STG = 32;
constexpr int BAR_DEAD = 33;
constexpr int BAR_X = 35;
constexpr int BAR_REL = 36;

constexpr int NB_G1DONE = 1;
constexpr int NB_OREADY = 2;
constexpr int NB_WG = 4;
constexpr int NB_HELP3 = 6;
constexpr int NB_FIRST = 7;
constexpr int NB_LEAD = 8;

#define PACE 390u
#define PF0 20
#define PEEL 1
#define IDLEW 1
#define LA0 3
#define LA1 4
#define STAG 12
#define LAST 0
#define FINE 40
#define POLL1 0
#define PIN 0
#define SCHED 1
#define REG_MATH 224
#define REG_HELP 56
constexpr int SPIN_LIMIT = 1 << 20;

__device__ __align__(1024) __nv_bfloat16 g_o[SEQ * DM];
__device__ uint32_t g_flag_o[256];
__device__ uint32_t g_flag_h[4];
__device__ uint4 g_halo[128 * 128];
__device__ __align__(128) const uint32_t g_tab[T_END / 4] = {
0x3c003c00,0x3bf13bff,0,0xafd6a648,0x3c003c00,0x3b993bce,0,0xb505b303,0x3c003c00,0x3af63b50,0,0xb7e3b67c,
0x3c003c00,0x3a0f3a8a,0,0xb93ab89b,0x3bc33bfe,0x3b773bfa,0xb3c6aa48,0xb5c2acb5,0x3a6d3b3b,0x389b3a4f,0xb8c4b6d7,0xba8ab8ec,
0x381d395f,0x26483505,0xbaddb9ed,0xbbffbb99,0x30b23564,0xb848b444,0xbbeabb88,0xbac2bbb6,0x3b0e3bf6,0x3a8a3bf1,0xb78bae46,0xb89bafd6,
0x34a53913,0xa6483732,0xbba8ba2f,0xbbffbb25,0xb78bae46,0xbac2b7e3,0xbb0ebbf6,0xb848baf6,0xbba8ba2f,0xbb50bbfa,0xb4a5b913,0x367cacb5,
0x39ed3bea,0x393a3be2,0xb95fb0b2,0xba0fb179,0xb56433c6,0xb8ec2648,0xbb88bbc3,0xba4fbbff,0xbbfeba6d,0xbb25bbce,0xaa48b8c4,0x3732b303,
0xb6d7badd,0x3444b67c,0x3b3b381d,0x3bb63b50,0x38723bd9,0x37323bce,0xbaa7b23e,0xbb25b303,0xbaa7b23e,0xbbb6b67c,0xb872bbd9,0xb444bb50,
0xb872bbd9,0xacb5ba8a,0x3aa7323e,0x3bfa389b,0x3aa7323e,0x3bf139cb,0x38723bd9,0xafd63984,0x35643bc3,0x33033bb6,0xbb88b3c6,0xbbceb444,
0xbbfeb8c4,0xbb77ba0f,0x2a48ba6d,0x35c2b93a,0x36d7b81d,0x3a8aafd6,0x3b3b3add,0x389b3bf1,0x395f3bea,0x26483b25,0xb9ed30b2,0xbbffb732,
0x2e463ba8,0xa6483b99,0xbbf6b4a5,0xbbffb505,0xba2fbb0e,0xb848bbb6,0x3913b78b,0x3ac2b444,0x3bf634a5,0x3b50393a,0x2e463ba8,0xb67c3a0f,
0xb913378b,0xbbe2afd6,0xba2fbb0e,0xb179bbf1,0xb0b23b88,0xb4443b77,0xbbeab564,0xbbb6b5c2,0xb3c6bbfe,0x2cb5bbe2,0x3bc3aa48,0x3bfa3179,
0x38c43b3b,0x2fd63bff,0xba6d36d7,0xbbf12648,0xbaddb95f,0xb505bbce,0x381db9ed,0x3b99b303,0xb61f3b64,0xb7e33b50,0xbb64b61f,0xbaf6b67c,
0x361fbb64,0x393aba8a,0x3b64361f,0x3a0f389b,0xb61f3b64,0xba4f3984,0xbb64b61f,0xb8ecb9cb,0x361fbb64,0x3b25b848,0x3b64361f,0x37323ac2,
0xb8c43b3b,0xb9843b25,0xba6db6d7,0xb9cbb732,0x3addb95f,0x3bceb7e3,0x381d39ed,0x33033af6,0xbbea3564,0xbb77acb5,0xb0b2bb88,0x35c2bbfa,
0x3bc32a48,0x389b38ec,0xb3c63bfe,0xba8a3a4f,0xba2f3b0e,0xbac23af6,0xb913b78b,0xb848b7e3,0x3bf6b4a5,0x3b50acb5,0xae463ba8,0xb67c3bfa,
0xb913b78b,0xb179ba4f,0x3a2fbb0e,0x3be2b8ec,0xae463ba8,0xb9cb3b99,0xbbf634a5,0xb984b505,0xbb3b3add,0xbb993ac2,0xb6d7b81d,0xb505b848,
0x39ed30b2,0x37e335c2,0xb95f3bea,0xbaf63b77,0x3564bbc3,0x3a0fbbe2,0x3b88b3c6,0x393a3179,0xbbfe38c4,0xba4f2648,0xaa48ba6d,0x38ecbbff,
0xbbd93aa7,0xbbfa3a8a,0xb23eb872,0xacb5b89b,0x323e3872,0xafd639cb,0xbbd93aa7,0xbbf13984,0x3bd9baa7,0x3b99b848,0x323e3872,0xb5053ac2,
0xb23eb872,0x37e3bb77,0x3bd9baa7,0x3af6b5c2,0xbbfe3a6d,0xbbe23a4f,0x2a48b8c4,0x3179b8ec,0xb6d73add,0xb9843b99,0xbb3b381d,0xb9cb3505,
0x395fb0b2,0x33033444,0xb9ed3bea,0xbbce3bb6,0x3b88bbc3,0x3b77b93a,0x356433c6,0xb5c23a0f,0xbba83a2f,0xbb503a0f,0x34a5b913,0x367cb93a,
0xbb0e3bf6,0xbbe23bf1,0xb78b2e46,0xb179afd6,0xb4a53913,0xb9cb3b25,0xbba83a2f,0xb9843732,0x378bae46,0xb30337e3,0xbb0e3bf6,0xbbce3af6,
0xbadd39ed,0xba4f39cb,0x381db95f,0x38ecb984,0xbbea3b88,0xbb253ac2,0x30b2b564,0x3732b848,0xbbc33bfe,0xbbb63b77,0xb3c62a48,0x3444b5c2,
0xba6d3b3b,0xbbfa3be2,0xb8c436d7,0x2cb5b179,0xb9a839a8,0xb8ec3984,0x39a8b9a8,0x3a4fb9cb,0xb9a839a8,0xb7323848,0x39a8b9a8,0x3b25bac2,
0xb9a839a8,0xb44435c2,0x39a8b9a8,0x3bb6bb77,0xb9a839a8,0xacb53179,0x39a8b9a8,0x3bfabbe2,0xb81d395f,0xb67c393a,0x3addb9ed,0x3b50ba0f,
0xb0b23564,0x31792fd6,0x3beabb88,0x3be2bbf1,0x33c6aa48,0x3984b732,0x3bc3bbfe,0x39cbbb25,0x38c4b6d7,0x3bcebaf6,0x3a6dbb3b,0x3303b7e3,
0xb4a53913,0xb17938ec,0x3ba8ba2f,0x3be2ba4f,0x378bae46,0x39cbb505,0x3b0ebbf6,0x3984bb99,0x3ba8ba2f,0x3bcebbb6,0x34a5b913,0xb303b444,
0x3b0ebbf6,0x35c2ba0f,0xb78b2e46,0xbb77393a,0xaa4838c4,0x2cb5389b,0x3bfeba6d,0x3bfaba8a,0x3b3bb81d,0x3bf1b984,0x36d7badd,0x2fd6b9cb,
0x39edbbea,0x3505bac2,0xb95f30b2,0xbb993848,0xb564b3c6,0xbaf635c2,0xbb883bc3,0xb7e33b77,0x323e3872,0x35053848,0x3bd9baa7,0x3b99bac2,
0x3bd9baa7,0x3af6bb77,0xb23eb872,0xb7e3b5c2,0xb23eb872,0xb93ab179,0xbbd93aa7,0xba0f3be2,0xbbd93aa7,0xb8ec3bff,0x323e3872,0x3a4fa648,
0x36d7381d,0x384837e3,0x3b3bbadd,0x3ac2baf6,0x395fbbea,0x367cbbfa,0xb9edb0b2,0xbb502cb5,0xbb8833c6,0xbbe238ec,0xb5643bc3,0x31793a4f,
0x2a483a6d,0x39843505,0x3bfeb8c4,0x39cbbb99,0x3913378b,0x39cb3732,0x3a2fbb0e,0x3984bb25,0x2e46bba8,0xb303baf6,0xbbf634a5,0xbbce37e3,
0xba2f3b0e,0xb5c23bfa,0x3913378b,0x3b772cb5,0x3bf6b4a5,0x3a8aba4f,0x2e46bba8,0xb89bb8ec,0x3a6d36d7,0x3af6367c,0x38c4bb3b,0x37e3bb50,
0xb81db9ed,0xba0fb89b,0xbadd395f,0xb93a3a8a,0x30b23b88,0x38ec39cb,0x3beab564,0x3a4fb984,0x33c6bbfe,0xb732bac2,0xbbc3aa48,0xbb253848,
0x3b64361f,0x3bb635c2,0x361fbb64,0x3444bb77,0xbb64b61f,0xbbfab179,0xb61f3b64,0xacb53be2,0x3b64361f,0x3bf1a648,0x361fbb64,0xafd6bbff,
0xbb64b61f,0xbb993303,0xb61f3b64,0x35053bce,0x3bea3564,0x3bff3505,0x30b2bb88,0x2648bb99,0xbbc32a48,0xbac23444,0x33c63bfe,0x38483bb6,
0x3a6db6d7,0x367cba0f,0xb8c4bb3b,0xbb50b93a,0xb81d39ed,0x31793bf1,0x3add395f,0x3be22fd6,0x3bf634a5,0x3bce3444,0xae46bba8,0xb303bbb6,
0xb913378b,0xb5c2393a,0x3a2f3b0e,0x3b773a0f,0xae46bba8,0xb89bbbf1,0xbbf6b4a5,0xba8a2fd6,0x3a2f3b0e,0x3bff3732,0x3913b78b,0xa648bb25,
0x3b8833c6,0x3b253303,0xb564bbc3,0xb732bbce,0xaa483a6d,0x34443b50,0x3bfe38c4,0x3bb6367c,0xbb3bbadd,0xbbfab89b,0xb6d7381d,0x2cb53a8a,
0x39edb0b2,0x2fd6b984,0xb95fbbea,0xbbf1b9cb,0x3aa7323e,0x3a0f3179,0xb872bbd9,0xb93abbe2,0x38723bd9,0x3a4f3bff,0x3aa7323e,0x38eca648,
0xbaa7b23e,0xb7323303,0x38723bd9,0x3b253bce,0xb872bbd9,0xbbb6bb50,0xbaa7b23e,0xb444367c,0x395f30b2,0x389b2fd6,0xb9edbbea,0xba8abbf1,
0x3b883bc3,0x3bff3b25,0x3564b3c6,0x2648b732,0x2a4838c4,0x38483af6,0x3bfe3a6d,0x3ac237e3,0xbb3bb81d,0xb67c2cb5,0x36d73add,0x3b503bfa,
0x378b2e46,0x35c22cb5,0xbb0ebbf6,0xbb77bbfa,0x3ba83a2f,0x3a8a38ec,0xb4a5b913,0xb89bba4f,0x3b0e3bf6,0x3bff3b99,0x378b2e46,0xa648b505,
0x34a53913,0x3ac23bb6,0x3ba83a2f,0x38483444,0x33c62a48,0x2fd62648,0xbbc3bbfe,0xbbf1bbff,0x38c436d7,0x35053303,0xba6dbb3b,0xbb99bbce,
0x3add39ed,0x37e3367c,0xb81db95f,0xbaf6bb50,0x3bea3b88,0x393a389b,0xb0b2b564,0xba0fba8a,0x3c003c00,0xbbf1bbff,0,0x2fd62648,
0x3c003c00,0xbb99bbce,0,0x35053303,0x3c003c00,0xbaf6bb50,0,0x37e3367c,0x3c003c00,0xba0fba8a,0,0x393a389b,
0x3bc33bfe,0xbb77bbfa,0xb3c6aa48,0x35c22cb5,0x3a6d3b3b,0xb89bba4f,0xb8c4b6d7,0x3a8a38ec,0x381d395f,0xa648b505,0xbaddb9ed,0x3bff3b99,
0x30b23564,0x38483444,0xbbeabb88,0x3ac23bb6,0x3b0e3bf6,0xba8abbf1,0xb78bae46,0x389b2fd6,0x34a53913,0x2648b732,0xbba8ba2f,0x3bff3b25,
0xb78bae46,0x3ac237e3,0xbb0ebbf6,0x38483af6,0xbba8ba2f,0x3b503bfa,0xb4a5b913,0xb67c2cb5,0x39ed3bea,0xb93abbe2,0xb95fb0b2,0x3a0f3179,
0xb56433c6,0x38eca648,0xbb88bbc3,0x3a4f3bff,0xbbfeba6d,0x3b253bce,0xaa48b8c4,0xb7323303,0xb6d7badd,0xb444367c,0x3b3b381d,0xbbb6bb50,
0x38723bd9,0xb732bbce,0xbaa7b23e,0x3b253303,0xbaa7b23e,0x3bb6367c,0xb872bbd9,0x34443b50,0xb872bbd9,0x2cb53a8a,0x3aa7323e,0xbbfab89b,
0x3aa7323e,0xbbf1b9cb,0x38723bd9,0x2fd6b984,0x35643bc3,0xb303bbb6,0xbb88b3c6,0x3bce3444,0xbbfeb8c4,0x3b773a0f,0x2a48ba6d,0xb5c2393a,
0x36d7b81d,0xba8a2fd6,0x3b3b3add,0xb89bbbf1,0x395f3bea,0xa648bb25,0xb9ed30b2,0x3bff3732,0x2e463ba8,0x2648bb99,0xbbf6b4a5,0x3bff3505,
0xba2fbb0e,0x38483bb6,0x3913b78b,0xbac23444,0x3bf634a5,0xbb50b93a,0x2e463ba8,0x367cba0f,0xb913378b,0x3be22fd6,0xba2fbb0e,0x31793bf1,
0xb0b23b88,0x3444bb77,0xbbeab564,0x3bb635c2,0xb3c6bbfe,0xacb53be2,0x3bc3aa48,0xbbfab179,0x38c43b3b,0xafd6bbff,0xba6d36d7,0x3bf1a648,
0xbaddb95f,0x35053bce,0x381db9ed,0xbb993303,0xb61f3b64,0x37e3bb50,0xbb64b61f,0x3af6367c,0x361fbb64,0xb93a3a8a,0x3b64361f,0xba0fb89b,
0xb61f3b64,0x3a4fb984,0xbb64b61f,0x38ec39cb,0x361fbb64,0xbb253848,0x3b64361f,0xb732bac2,0xb8c43b3b,0x3984bb25,0xba6db6d7,0x39cb3732,
0x3addb95f,0xbbce37e3,0x381d39ed,0xb303baf6,0xbbea3564,0x3b772cb5,0xb0b2bb88,0xb5c23bfa,0x3bc32a48,0xb89bb8ec,0xb3c63bfe,0x3a8aba4f,
0xba2f3b0e,0x3ac2baf6,0xb913b78b,0x384837e3,0x3bf6b4a5,0xbb502cb5,0xae463ba8,0x367cbbfa,0xb913b78b,0x31793a4f,0x3a2fbb0e,0xbbe238ec,
0xae463ba8,0x39cbbb99,0xbbf634a5,0x39843505,0xbb3b3add,0x3b99bac2,0xb6d7b81d,0x35053848,0x39ed30b2,0xb7e3b5c2,0xb95f3bea,0x3af6bb77,
0x3564bbc3,0xba0f3be2,0x3b88b3c6,0xb93ab179,0xbbfe38c4,0x3a4fa648,0xaa48ba6d,0xb8ec3bff,0xbbd93aa7,0x3bfaba8a,0xb23eb872,0x2cb5389b,
0x323e3872,0x2fd6b9cb,0xbbd93aa7,0x3bf1b984,0x3bd9baa7,0xbb993848,0x323e3872,0x3505bac2,0xb23eb872,0xb7e33b77,0x3bd9baa7,0xbaf635c2,
0xbbfe3a6d,0x3be2ba4f,0x2a48b8c4,0xb17938ec,0xb6d73add,0x3984bb99,0xbb3b381d,0x39cbb505,0x395fb0b2,0xb303b444,0xb9ed3bea,0x3bcebbb6,
0x3b88bbc3,0xbb77393a,0x356433c6,0x35c2ba0f,0xbba83a2f,0x3b50ba0f,0x34a5b913,0xb67c393a,0xbb0e3bf6,0x3be2bbf1,0xb78b2e46,0x31792fd6,
0xb4a53913,0x39cbbb25,0xbba83a2f,0x3984b732,0x378bae46,0x3303b7e3,0xbb0e3bf6,0x3bcebaf6,0xbadd39ed,0x3a4fb9cb,0x381db95f,0xb8ec3984,
0xbbea3b88,0x3b25bac2,0x30b2b564,0xb7323848,0xbbc33bfe,0x3bb6bb77,0xb3c62a48,0xb44435c2,0xba6d3b3b,0x3bfabbe2,0xb8c436d7,0xacb53179,
0xb9a839a8,0x38ecb984,0x39a8b9a8,0xba4f39cb,0xb9a839a8,0x3732b848,0x39a8b9a8,0xbb253ac2,0xb9a839a8,0x3444b5c2,0x39a8b9a8,0xbbb63b77,
0xb9a839a8,0x2cb5b179,0x39a8b9a8,0xbbfa3be2,0xb81d395f,0x367cb93a,0x3addb9ed,0xbb503a0f,0xb0b23564,0xb179afd6,0x3beabb88,0xbbe23bf1,
0x33c6aa48,0xb9843732,0x3bc3bbfe,0xb9cb3b25,0x38c4b6d7,0xbbce3af6,0x3a6dbb3b,0xb30337e3,0xb4a53913,0x3179b8ec,0x3ba8ba2f,0xbbe23a4f,
0x378bae46,0xb9cb3505,0x3b0ebbf6,0xb9843b99,0x3ba8ba2f,0xbbce3bb6,0x34a5b913,0x33033444,0x3b0ebbf6,0xb5c23a0f,0xb78b2e46,0x3b77b93a,
0xaa4838c4,0xacb5b89b,0x3bfeba6d,0xbbfa3a8a,0x3b3bb81d,0xbbf13984,0x36d7badd,0xafd639cb,0x39edbbea,0xb5053ac2,0xb95f30b2,0x3b99b848,
0xb564b3c6,0x3af6b5c2,0xbb883bc3,0x37e3bb77,0x323e3872,0xb505b848,0x3bd9baa7,0xbb993ac2,0x3bd9baa7,0xbaf63b77,0xb23eb872,0x37e335c2,
0xb23eb872,0x393a3179,0xbbd93aa7,0x3a0fbbe2,0xbbd93aa7,0x38ecbbff,0x323e3872,0xba4f2648,0x36d7381d,0xb848b7e3,0x3b3bbadd,0xbac23af6,
0x395fbbea,0xb67c3bfa,0xb9edb0b2,0x3b50acb5,0xbb8833c6,0x3be2b8ec,0xb5643bc3,0xb179ba4f,0x2a483a6d,0xb984b505,0x3bfeb8c4,0xb9cb3b99,
0x3913378b,0xb9cbb732,0x3a2fbb0e,0xb9843b25,0x2e46bba8,0x33033af6,0xbbf634a5,0x3bceb7e3,0xba2f3b0e,0x35c2bbfa,0x3913378b,0xbb77acb5,
0x3bf6b4a5,0xba8a3a4f,0x2e46bba8,0x389b38ec,0x3a6d36d7,0xbaf6b67c,0x38c4bb3b,0xb7e33b50,0xb81db9ed,0x3a0f389b,0xbadd395f,0x393aba8a,
0x30b23b88,0xb8ecb9cb,0x3beab564,0xba4f3984,0x33c6bbfe,0x37323ac2,0xbbc3aa48,0x3b25b848,0x3b64361f,0xbbb6b5c2,0x361fbb64,0xb4443b77,
0xbb64b61f,0x3bfa3179,0xb61f3b64,0x2cb5bbe2,0x3b64361f,0xbbf12648,0x361fbb64,0x2fd63bff,0xbb64b61f,0x3b99b303,0xb61f3b64,0xb505bbce,
0x3bea3564,0xbbffb505,0x30b2bb88,0xa6483b99,0xbbc32a48,0x3ac2b444,0x33c63bfe,0xb848bbb6,0x3a6db6d7,0xb67c3a0f,0xb8c4bb3b,0x3b50393a,
0xb81d39ed,0xb179bbf1,0x3add395f,0xbbe2afd6,0x3bf634a5,0xbbceb444,0xae46bba8,0x33033bb6,0xb913378b,0x35c2b93a,0x3a2f3b0e,0xbb77ba0f,
0xae46bba8,0x389b3bf1,0xbbf6b4a5,0x3a8aafd6,0x3a2f3b0e,0xbbffb732,0x3913b78b,0x26483b25,0x3b8833c6,0xbb25b303,0xb564bbc3,0x37323bce,
0xaa483a6d,0xb444bb50,0x3bfe38c4,0xbbb6b67c,0xbb3bbadd,0x3bfa389b,0xb6d7381d,0xacb5ba8a,0x39edb0b2,0xafd63984,0xb95fbbea,0x3bf139cb,
0x3aa7323e,0xba0fb179,0xb872bbd9,0x393a3be2,0x38723bd9,0xba4fbbff,0x3aa7323e,0xb8ec2648,0xbaa7b23e,0x3732b303,0x38723bd9,0xbb25bbce,
0xb872bbd9,0x3bb63b50,0xbaa7b23e,0x3444b67c,0x395f30b2,0xb89bafd6,0xb9edbbea,0x3a8a3bf1,0x3b883bc3,0xbbffbb25,0x3564b3c6,0xa6483732,
0x2a4838c4,0xb848baf6,0x3bfe3a6d,0xbac2b7e3,0xbb3bb81d,0x367cacb5,0x36d73add,0xbb50bbfa,0x378b2e46,0xb5c2acb5,0xbb0ebbf6,0x3b773bfa,
0x3ba83a2f,0xba8ab8ec,0xb4a5b913,0x389b3a4f,0x3b0e3bf6,0xbbffbb99,0x378b2e46,0x26483505,0x34a53913,0xbac2bbb6,0x3ba83a2f,0xb848b444,
0x33c62a48,0xafd6a648,0xbbc3bbfe,0x3bf13bff,0x38c436d7,0xb505b303,0xba6dbb3b,0x3b993bce,0x3add39ed,0xb7e3b67c,0xb81db95f,0x3af63b50,
0x3bea3b88,0xb93ab89b,0xb0b2b564,0x3a0f3a8a,0x3c003c00,0x38ec3984,0,0xba4fb9cb,0x3c003c00,0x37323848,0,0xbb25bac2,
0x3c003c00,0x344435c2,0,0xbbb6bb77,0x3c003c00,0x2cb53179,0,0xbbfabbe2,0xb3c6aa48,0xbb50ba0f,0xbbc3bbfe,0xb67cb93a,
0xb8c4b6d7,0xbbe2bbf1,0xba6dbb3b,0x3179afd6,0xbaddb9ed,0xb9cbbb25,0xb81db95f,0x39843732,0xbbeabb88,0xb303b7e3,0xb0b2b564,0x3bce3af6,
0xbb0ebbf6,0xb179b8ec,0x378b2e46,0x3be23a4f,0xb4a5b913,0x39cb3505,0x3ba83a2f,0x39843b99,0x378b2e46,0x3bce3bb6,0x3b0e3bf6,0xb3033444,
0x3ba83a2f,0x35c23a0f,0x34a53913,0xbb77b93a,0x395f30b2,0x3bfa3a8a,0x39ed3bea,0xacb5389b,0x3b883bc3,0x2fd639cb,0xb56433c6,0xbbf1b984,
0x2a4838c4,0xbb99b848,0xbbfeba6d,0xb505bac2,0xbb3bb81d,0xb7e3bb77,0xb6d7badd,0x3af635c2,0x38723bd9,0xb5053848,0xbaa7b23e,0xbb99bac2,
0xbaa7b23e,0xbaf6bb77,0xb872bbd9,0x37e3b5c2,0xb872bbd9,0x393ab179,0x3aa7323e,0x3a0f3be2,0x3aa7323e,0x38ec3bff,0x38723bd9,0xba4fa648,
0xbb88b3c6,0xbac2baf6,0xb564bbc3,0x3848b7e3,0x2a48ba6d,0x3b502cb5,0x3bfe38c4,0x367c3bfa,0x3b3b3add,0xb1793a4f,0xb6d7381d,0xbbe2b8ec,
0xb9ed30b2,0xb9cbbb99,0xb95fbbea,0x3984b505,0xae46bba8,0x39cbb732,0x3bf634a5,0x39843b25,0x3a2f3b0e,0xb3033af6,0xb913378b,0xbbceb7e3,
0xbbf6b4a5,0xb5c2bbfa,0xae46bba8,0x3b77acb5,0x3913b78b,0x3a8a3a4f,0x3a2f3b0e,0xb89b38ec,0x3bea3564,0x37e33b50,0xb0b23b88,0xbaf6367c,
0xbbc32a48,0xb93aba8a,0xb3c6bbfe,0x3a0fb89b,0x3a6db6d7,0x3a4f3984,0x38c43b3b,0xb8ec39cb,0xb81d39ed,0xbb25b848,0xbaddb95f,0x3732bac2,
0xb61f3b64,0xbbb635c2,0xbb64b61f,0xb444bb77,0x361fbb64,0x3bfab179,0x3b64361f,0x2cb53be2,0xb61f3b64,0xbbf1a648,0xbb64b61f,0x2fd6bbff,
0x361fbb64,0x3b993303,0x3b64361f,0xb5053bce,0xba6db6d7,0xa648bb99,0x38c4bb3b,0x3bffb505,0x381d39ed,0xb8483bb6,0xbadd395f,0xbac2b444,
0xb0b2bb88,0x3b50b93a,0x3beab564,0x367c3a0f,0xb3c63bfe,0xbbe22fd6,0xbbc3aa48,0x3179bbf1,0x3a2fbb0e,0x3bceb444,0x3913378b,0xb3033bb6,
0xbbf634a5,0xb5c2b93a,0x2e46bba8,0x3b77ba0f,0x3913378b,0xb89b3bf1,0xba2f3b0e,0xba8aafd6,0x2e46bba8,0x3bffb732,0x3bf6b4a5,0xa6483b25,
0x36d7381d,0xb7323bce,0xbb3b3add,0xbb253303,0x395fbbea,0x3bb6b67c,0x39ed30b2,0xb4443b50,0xbb8833c6,0x2cb5ba8a,0x3564bbc3,0x3bfab89b,
0x2a483a6d,0xbbf139cb,0xbbfe38c4,0xafd6b984,0xbbd93aa7,0xba0f3179,0xb23eb872,0x393abbe2,0x323e3872,0xba4f3bff,0xbbd93aa7,0xb8eca648,
0x3bd9baa7,0x37323303,0x323e3872,0xbb253bce,0xb23eb872,0x3bb6bb50,0x3bd9baa7,0x3444367c,0x2a48b8c4,0x3a8abbf1,0x3bfeba6d,0x389bafd6,
0xbb3b381d,0xa648b732,0x36d7badd,0x3bffbb25,0xb9ed3bea,0xbac237e3,0xb95f30b2,0x3848baf6,0x356433c6,0xbb503bfa,0xbb883bc3,0xb67cacb5,
0x3ba8ba2f,0x35c2acb5,0xb4a53913,0xbb773bfa,0x3b0ebbf6,0x3a8ab8ec,0x378bae46,0xb89b3a4f,0x34a5b913,0x3bffbb99,0x3ba8ba2f,0xa6483505,
0xb78b2e46,0x3ac2bbb6,0x3b0ebbf6,0x3848b444,0xb81d395f,0xbbf13bff,0xbadd39ed,0xafd62648,0xb0b23564,0xbb993bce,0xbbea3b88,0xb5053303,
0x33c6aa48,0xbaf63b50,0xbbc33bfe,0xb7e3367c,0x38c4b6d7,0xba0f3a8a,0xba6d3b3b,0xb93a389b,0xb9a839a8,0x2fd6a648,0x39a8b9a8,0x3bf1bbff,
0xb9a839a8,0x3505b303,0x39a8b9a8,0x3b99bbce,0xb9a839a8,0x37e3b67c,0x39a8b9a8,0x3af6bb50,0xb9a839a8,0x393ab89b,0x39a8b9a8,0x3a0fba8a,
0x3addb9ed,0x3b77bbfa,0x381db95f,0xb5c22cb5,0x3beabb88,0x389bba4f,0x30b2b564,0xba8a38ec,0x3bc3bbfe,0x2648b505,0xb3c62a48,0xbbff3b99,
0x3a6dbb3b,0xb8483444,0xb8c436d7,0xbac23bb6,0x34a5b913,0xb89b2fd6,0xbba83a2f,0xba8a3bf1,0xb78b2e46,0xbbff3b25,0xbb0e3bf6,0x26483732,
0xbba83a2f,0xb8483af6,0xb4a53913,0x3ac2b7e3,0xbb0e3bf6,0x367c2cb5,0x378bae46,0x3b50bbfa,0xbbfe3a6d,0xb93a3be2,0xaa4838c4,0x3a0fb179,
0xb6d73add,0x38ec2648,0x3b3bb81d,0x3a4fbbff,0x395fb0b2,0x3b25bbce,0x39edbbea,0xb732b303,0x3b88bbc3,0xb444b67c,0xb564b3c6,0xbbb63b50,
0x323e3872,0x3b25b303,0x3bd9baa7,0x3732bbce,0x3bd9baa7,0x3444bb50,0xb23eb872,0xbbb6367c,0xb23eb872,0xbbfa389b,0xbbd93aa7,0xacb53a8a,
0xbbd93aa7,0x2fd63984,0x323e3872,0x3bf1b9cb,0x3b3bbadd,0x3303bbb6,0xb6d7b81d,0xbbce3444,0xb9edb0b2,0xbb773a0f,0xb95f3bea,0x35c2393a,
0xb5643bc3,0x3a8a2fd6,0x3b88b3c6,0x389bbbf1,0x3bfeb8c4,0x2648bb25,0xaa48ba6d,0xbbff3732,0xb913b78b,0xbbff3505,0xba2f3b0e,0x26483b99,
0xae463ba8,0x3ac23444,0x3bf6b4a5,0x3848bbb6,0x3a2fbb0e,0xb67cba0f,0xb913b78b,0xbb50393a,0xbbf634a5,0xb1793bf1,0xae463ba8,0x3be2afd6,
0xb8c43b3b,0x34443b77,0x3a6d36d7,0x3bb6b5c2,0x3addb95f,0xacb5bbe2,0xb81db9ed,0xbbfa3179,0xbbea3564,0xafd63bff,0x30b23b88,0x3bf12648,
0x3bc32a48,0x3505bbce,0x33c6bbfe,0xbb99b303,0x3b64361f,0x3af6b67c,0x361fbb64,0xb7e3bb50,0xbb64b61f,0xba0f389b,0xb61f3b64,0x393a3a8a,
0x3b64361f,0x38ecb9cb,0x361fbb64,0xba4fb984,0xbb64b61f,0xb7323ac2,0xb61f3b64,0x3b253848,0x30b2bb88,0xb984bb25,0xbbeab564,0xb9cb3732,
0x33c63bfe,0x3bce37e3,0x3bc3aa48,0x3303baf6,0xb8c4bb3b,0xbb772cb5,0xba6d36d7,0x35c23bfa,0x3add395f,0x389bb8ec,0x381db9ed,0xba8aba4f,
0xbbf6b4a5,0xb84837e3,0x2e463ba8,0x3ac23af6,0x3913b78b,0xb67cbbfa,0xba2fbb0e,0xbb50acb5,0x2e463ba8,0x3be238ec,0x3bf634a5,0x3179ba4f,
0xba2fbb0e,0xb9843505,0xb913378b,0x39cb3b99,0x35643bc3,0x3b993ac2,0x3b8833c6,0x3505b848,0xbbfeb8c4,0xb7e335c2,0xaa483a6d,0x3af63b77,
0x36d7b81d,0xba0fbbe2,0xbb3bbadd,0xb93a3179,0x395f3bea,0x3a4f2648,0x39edb0b2,0xb8ecbbff,0x3aa7323e,0x2cb5b89b,0xb872bbd9,0xbbfaba8a,
0x38723bd9,0x3bf13984,0x3aa7323e,0xafd6b9cb,0xbaa7b23e,0x35053ac2,0x38723bd9,0x3b993848,0xb872bbd9,0xbaf6b5c2,0xbaa7b23e,0x37e33b77,
0xb9edbbea,0xbbe2ba4f,0xb95fb0b2,0x317938ec,0x3564b3c6,0xb984bb99,0xbb88bbc3,0xb9cbb505,0x3bfe3a6d,0x3303b444,0xaa48b8c4,0xbbcebbb6,
0x36d73add,0x3b77393a,0x3b3b381d,0xb5c2ba0f,0xb78bae46,0x367c393a,0x3b0e3bf6,0x3b503a0f,0xbba8ba2f,0xb1792fd6,0x34a53913,0x3be23bf1,
0xbb0ebbf6,0xb984b732,0xb78bae46,0x39cb3b25,0xb4a5b913,0xbbcebaf6,0xbba8ba2f,0x330337e3,0x3bc33bfe,0x3a4f39cb,0x33c62a48,0xb8ecb984,
0x3a6d3b3b,0x3b253ac2,0x38c436d7,0xb732b848,0x381d395f,0x3bb63b77,0x3add39ed,0xb444b5c2,0x30b23564,0x3bfa3be2,0x3bea3b88,0xacb5b179,
0x3c003c00,0xb8ecb984,0,0x3a4f39cb,0x3c003c00,0xb732b848,0,0x3b253ac2,0x3c003c00,0xb444b5c2,0,0x3bb63b77,
0x3c003c00,0xacb5b179,0,0x3bfa3be2,0xb3c6aa48,0x3b503a0f,0xbbc3bbfe,0x367c393a,0xb8c4b6d7,0x3be23bf1,0xba6dbb3b,0xb1792fd6,
0xbaddb9ed,0x39cb3b25,0xb81db95f,0xb984b732,0xbbeabb88,0x330337e3,0xb0b2b564,0xbbcebaf6,0xbb0ebbf6,0x317938ec,0x378b2e46,0xbbe2ba4f,
0xb4a5b913,0xb9cbb505,0x3ba83a2f,0xb984bb99,0x378b2e46,0xbbcebbb6,0x3b0e3bf6,0x3303b444,0x3ba83a2f,0xb5c2ba0f,0x34a53913,0x3b77393a,
0x395f30b2,0xbbfaba8a,0x39ed3bea,0x2cb5b89b,0x3b883bc3,0xafd6b9cb,0xb56433c6,0x3bf13984,0x2a4838c4,0x3b993848,0xbbfeba6d,0x35053ac2,
0xbb3bb81d,0x37e33b77,0xb6d7badd,0xbaf6b5c2,0x38723bd9,0x3505b848,0xbaa7b23e,0x3b993ac2,0xbaa7b23e,0x3af63b77,0xb872bbd9,0xb7e335c2,
0xb872bbd9,0xb93a3179,0x3aa7323e,0xba0fbbe2,0x3aa7323e,0xb8ecbbff,0x38723bd9,0x3a4f2648,0xbb88b3c6,0x3ac23af6,0xb564bbc3,0xb84837e3,
0x2a48ba6d,0xbb50acb5,0x3bfe38c4,0xb67cbbfa,0x3b3b3add,0x3179ba4f,0xb6d7381d,0x3be238ec,0xb9ed30b2,0x39cb3b99,0xb95fbbea,0xb9843505,
0xae46bba8,0xb9cb3732,0x3bf634a5,0xb984bb25,0x3a2f3b0e,0x3303baf6,0xb913378b,0x3bce37e3,0xbbf6b4a5,0x35c23bfa,0xae46bba8,0xbb772cb5,
0x3913b78b,0xba8aba4f,0x3a2f3b0e,0x389bb8ec,0x3bea3564,0xb7e3bb50,0xb0b23b88,0x3af6b67c,0xbbc32a48,0x393a3a8a,0xb3c6bbfe,0xba0f389b,
0x3a6db6d7,0xba4fb984,0x38c43b3b,0x38ecb9cb,0xb81d39ed,0x3b253848,0xbaddb95f,0xb7323ac2,0xb61f3b64,0x3bb6b5c2,0xbb64b61f,0x34443b77,
0x361fbb64,0xbbfa3179,0x3b64361f,0xacb5bbe2,0xb61f3b64,0x3bf12648,0xbb64b61f,0xafd63bff,0x361fbb64,0xbb99b303,0x3b64361f,0x3505bbce,
0xba6db6d7,0x26483b99,0x38c4bb3b,0xbbff3505,0x381d39ed,0x3848bbb6,0xbadd395f,0x3ac23444,0xb0b2bb88,0xbb50393a,0x3beab564,0xb67cba0f,
0xb3c63bfe,0x3be2afd6,0xbbc3aa48,0xb1793bf1,0x3a2fbb0e,0xbbce3444,0x3913378b,0x3303bbb6,0xbbf634a5,0x35c2393a,0x2e46bba8,0xbb773a0f,
0x3913378b,0x389bbbf1,0xba2f3b0e,0x3a8a2fd6,0x2e46bba8,0xbbff3732,0x3bf6b4a5,0x2648bb25,0x36d7381d,0x3732bbce,0xbb3b3add,0x3b25b303,
0x395fbbea,0xbbb6367c,0x39ed30b2,0x3444bb50,0xbb8833c6,0xacb53a8a,0x3564bbc3,0xbbfa389b,0x2a483a6d,0x3bf1b9cb,0xbbfe38c4,0x2fd63984,
0xbbd93aa7,0x3a0fb179,0xb23eb872,0xb93a3be2,0x323e3872,0x3a4fbbff,0xbbd93aa7,0x38ec2648,0x3bd9baa7,0xb732b303,0x323e3872,0x3b25bbce,
0xb23eb872,0xbbb63b50,0x3bd9baa7,0xb444b67c,0x2a48b8c4,0xba8a3bf1,0x3bfeba6d,0xb89b2fd6,0xbb3b381d,0x26483732,0x36d7badd,0xbbff3b25,
0xb9ed3bea,0x3ac2b7e3,0xb95f30b2,0xb8483af6,0x356433c6,0x3b50bbfa,0xbb883bc3,0x367c2cb5,0x3ba8ba2f,0xb5c22cb5,0xb4a53913,0x3b77bbfa,
0x3b0ebbf6,0xba8a38ec,0x378bae46,0x389bba4f,0x34a5b913,0xbbff3b99,0x3ba8ba2f,0x2648b505,0xb78b2e46,0xbac23bb6,0x3b0ebbf6,0xb8483444,
0xb81d395f,0x3bf1bbff,0xbadd39ed,0x2fd6a648,0xb0b23564,0x3b99bbce,0xbbea3b88,0x3505b303,0x33c6aa48,0x3af6bb50,0xbbc33bfe,0x37e3b67c,
0x38c4b6d7,0x3a0fba8a,0xba6d3b3b,0x393ab89b,0xb9a839a8,0xafd62648,0x39a8b9a8,0xbbf13bff,0xb9a839a8,0xb5053303,0x39a8b9a8,0xbb993bce,
0xb9a839a8,0xb7e3367c,0x39a8b9a8,0xbaf63b50,0xb9a839a8,0xb93a389b,0x39a8b9a8,0xba0f3a8a,0x3addb9ed,0xbb773bfa,0x381db95f,0x35c2acb5,
0x3beabb88,0xb89b3a4f,0x30b2b564,0x3a8ab8ec,0x3bc3bbfe,0xa6483505,0xb3c62a48,0x3bffbb99,0x3a6dbb3b,0x3848b444,0xb8c436d7,0x3ac2bbb6,
0x34a5b913,0x389bafd6,0xbba83a2f,0x3a8abbf1,0xb78b2e46,0x3bffbb25,0xbb0e3bf6,0xa648b732,0xbba83a2f,0x3848baf6,0xb4a53913,0xbac237e3,
0xbb0e3bf6,0xb67cacb5,0x378bae46,0xbb503bfa,0xbbfe3a6d,0x393abbe2,0xaa4838c4,0xba0f3179,0xb6d73add,0xb8eca648,0x3b3bb81d,0xba4f3bff,
0x395fb0b2,0xbb253bce,0x39edbbea,0x37323303,0x3b88bbc3,0x3444367c,0xb564b3c6,0x3bb6bb50,0x323e3872,0xbb253303,0x3bd9baa7,0xb7323bce,
0x3bd9baa7,0xb4443b50,0xb23eb872,0x3bb6b67c,0xb23eb872,0x3bfab89b,0xbbd93aa7,0x2cb5ba8a,0xbbd93aa7,0xafd6b984,0x323e3872,0xbbf139cb,
0x3b3bbadd,0xb3033bb6,0xb6d7b81d,0x3bceb444,0xb9edb0b2,0x3b77ba0f,0xb95f3bea,0xb5c2b93a,0xb5643bc3,0xba8aafd6,0x3b88b3c6,0xb89b3bf1,
0x3bfeb8c4,0xa6483b25,0xaa48ba6d,0x3bffb732,0xb913b78b,0x3bffb505,0xba2f3b0e,0xa648bb99,0xae463ba8,0xbac2b444,0x3bf6b4a5,0xb8483bb6,
0x3a2fbb0e,0x367c3a0f,0xb913b78b,0x3b50b93a,0xbbf634a5,0x3179bbf1,0xae463ba8,0xbbe22fd6,0xb8c43b3b,0xb444bb77,0x3a6d36d7,0xbbb635c2,
0x3addb95f,0x2cb53be2,0xb81db9ed,0x3bfab179,0xbbea3564,0x2fd6bbff,0x30b23b88,0xbbf1a648,0x3bc32a48,0xb5053bce,0x33c6bbfe,0x3b993303,
0x3b64361f,0xbaf6367c,0x361fbb64,0x37e33b50,0xbb64b61f,0x3a0fb89b,0xb61f3b64,0xb93aba8a,0x3b64361f,0xb8ec39cb,0x361fbb64,0x3a4f3984,
0xbb64b61f,0x3732bac2,0xb61f3b64,0xbb25b848,0x30b2bb88,0x39843b25,0xbbeab564,0x39cbb732,0x33c63bfe,0xbbceb7e3,0x3bc3aa48,0xb3033af6,
0xb8c4bb3b,0x3b77acb5,0xba6d36d7,0xb5c2bbfa,0x3add395f,0xb89b38ec,0x381db9ed,0x3a8a3a4f,0xbbf6b4a5,0x3848b7e3,0x2e463ba8,0xbac2baf6,
0x3913b78b,0x367c3bfa,0xba2fbb0e,0x3b502cb5,0x2e463ba8,0xbbe2b8ec,0x3bf634a5,0xb1793a4f,0xba2fbb0e,0x3984b505,0xb913378b,0xb9cbbb99,
0x35643bc3,0xbb99bac2,0x3b8833c6,0xb5053848,0xbbfeb8c4,0x37e3b5c2,0xaa483a6d,0xbaf6bb77,0x36d7b81d,0x3a0f3be2,0xbb3bbadd,0x393ab179,
0x395f3bea,0xba4fa648,0x39edb0b2,0x38ec3bff,0x3aa7323e,0xacb5389b,0xb872bbd9,0x3bfa3a8a,0x38723bd9,0xbbf1b984,0x3aa7323e,0x2fd639cb,
0xbaa7b23e,0xb505bac2,0x38723bd9,0xbb99b848,0xb872bbd9,0x3af635c2,0xbaa7b23e,0xb7e3bb77,0xb9edbbea,0x3be23a4f,0xb95fb0b2,0xb179b8ec,
0x3564b3c6,0x39843b99,0xbb88bbc3,0x39cb3505,0x3bfe3a6d,0xb3033444,0xaa48b8c4,0x3bce3bb6,0x36d73add,0xbb77b93a,0x3b3b381d,0x35c23a0f,
0xb78bae46,0xb67cb93a,0x3b0e3bf6,0xbb50ba0f,0xbba8ba2f,0x3179afd6,0x34a53913,0xbbe2bbf1,0xbb0ebbf6,0x39843732,0xb78bae46,0xb9cbbb25,
0xb4a5b913,0x3bce3af6,0xbba8ba2f,0xb303b7e3,0x3bc33bfe,0xba4fb9cb,0x33c62a48,0x38ec3984,0x3a6d3b3b,0xbb25bac2,0x38c436d7,0x37323848,
0x381d395f,0xbbb6bb77,0x3add39ed,0x344435c2,0x30b23564,0xbbfabbe2,0x3bea3b88,0x2cb53179,0x3c003c00,0xafd6a648,0,0xbbf1bbff,
0x3c003c00,0xb505b303,0,0xbb99bbce,0x3c003c00,0xb7e3b67c,0,0xbaf6bb50,0x3c003c00,0xb93ab89b,0,0xba0fba8a,
0xbbc3bbfe,0x35c22cb5,0x33c62a48,0x3b773bfa,0xba6dbb3b,0x3a8a38ec,0x38c436d7,0x389b3a4f,0xb81db95f,0x3bff3b99,0x3add39ed,0x26483505,
0xb0b2b564,0x3ac23bb6,0x3bea3b88,0xb848b444,0x3b0e3bf6,0xb89bafd6,0xb78bae46,0xba8abbf1,0x34a53913,0xbbffbb25,0xbba8ba2f,0x2648b732,
0xb78bae46,0xb848baf6,0xbb0ebbf6,0x3ac237e3,0xbba8ba2f,0x367cacb5,0xb4a5b913,0x3b503bfa,0xb9edbbea,0x3a0f3179,0x395f30b2,0x393a3be2,
0x3564b3c6,0x3a4f3bff,0x3b883bc3,0xb8ec2648,0x3bfe3a6d,0xb7323303,0x2a4838c4,0xbb25bbce,0x36d73add,0xbbb6bb50,0xbb3bb81d,0x3444b67c,
0x38723bd9,0xbb25b303,0xbaa7b23e,0xb732bbce,0xbaa7b23e,0xb444bb50,0xb872bbd9,0x3bb6367c,0xb872bbd9,0x3bfa389b,0x3aa7323e,0x2cb53a8a,
0x3aa7323e,0xafd63984,0x38723bd9,0xbbf1b9cb,0xb564bbc3,0x3bce3444,0x3b8833c6,0x33033bb6,0x3bfe38c4,0xb5c2393a,0xaa483a6d,0xbb77ba0f,
0xb6d7381d,0xb89bbbf1,0xbb3bbadd,0x3a8aafd6,0xb95fbbea,0x3bff3732,0x39edb0b2,0x26483b25,0x2e463ba8,0xbbffb505,0xbbf6b4a5,0x2648bb99,
0xba2fbb0e,0x3ac2b444,0x3913b78b,0x38483bb6,0x3bf634a5,0xb67c3a0f,0x2e463ba8,0xbb50b93a,0xb913378b,0xb179bbf1,0xba2fbb0e,0x3be22fd6,
0x30b2bb88,0x3bb635c2,0x3bea3564,0xb4443b77,0x33c63bfe,0xbbfab179,0xbbc32a48,0x2cb5bbe2,0xb8c4bb3b,0x3bf1a648,0x3a6db6d7,0x2fd63bff,
0x3add395f,0xbb993303,0xb81d39ed,0xb505bbce,0xb61f3b64,0xbaf6b67c,0xbb64b61f,0x37e3bb50,0x361fbb64,0x3a0f389b,0x3b64361f,0xb93a3a8a,
0xb61f3b64,0xb8ecb9cb,0xbb64b61f,0x3a4fb984,0x361fbb64,0x37323ac2,0x3b64361f,0xbb253848,0x38c4bb3b,0x39cb3732,0x3a6d36d7,0xb9843b25,
0xbadd395f,0xb303baf6,0xb81db9ed,0x3bceb7e3,0x3beab564,0xb5c23bfa,0x30b23b88,0xbb77acb5,0xbbc3aa48,0x3a8aba4f,0x33c6bbfe,0x389b38ec,
0xba2f3b0e,0xb848b7e3,0xb913b78b,0x3ac2baf6,0x3bf6b4a5,0xb67c3bfa,0xae463ba8,0xbb502cb5,0xb913b78b,0x3be2b8ec,0x3a2fbb0e,0x31793a4f,
0xae463ba8,0xb984b505,0xbbf634a5,0x39cbbb99,0x3b3bbadd,0x35053848,0x36d7381d,0xbb993ac2,0xb9edb0b2,0x3af6bb77,0x395fbbea,0x37e335c2,
0xb5643bc3,0xb93ab179,0xbb8833c6,0x3a0fbbe2,0x3bfeb8c4,0xb8ec3bff,0x2a483a6d,0xba4f2648,0xbbd93aa7,0xacb5b89b,0xb23eb872,0x3bfaba8a,
0x323e3872,0xbbf13984,0xbbd93aa7,0x2fd6b9cb,0x3bd9baa7,0xb5053ac2,0x323e3872,0xbb993848,0xb23eb872,0x3af6b5c2,0x3bd9baa7,0xb7e33b77,
0x3bfeba6d,0xb17938ec,0xaa4838c4,0xbbe23a4f,0x36d7badd,0x39cbb505,0x3b3bb81d,0xb9843b99,0xb95f30b2,0x3bcebbb6,0x39edbbea,0x33033444,
0xbb883bc3,0x35c2ba0f,0xb564b3c6,0x3b77b93a,0xbba83a2f,0x367cb93a,0x34a5b913,0x3b50ba0f,0xbb0e3bf6,0xb179afd6,0xb78b2e46,0x3be2bbf1,
0xb4a53913,0xb9843732,0xbba83a2f,0x39cbbb25,0x378bae46,0xbbce3af6,0xbb0e3bf6,0x3303b7e3,0x3addb9ed,0xb8ec3984,0xb81d395f,0xba4f39cb,
0x3beabb88,0xb7323848,0xb0b23564,0xbb253ac2,0x3bc3bbfe,0xb44435c2,0x33c6aa48,0xbbb63b77,0x3a6dbb3b,0xacb53179,0x38c4b6d7,0xbbfa3be2,
0xb9a839a8,0x3a4fb9cb,0x39a8b9a8,0x38ecb984,0xb9a839a8,0x3b25bac2,0x39a8b9a8,0x3732b848,0xb9a839a8,0x3bb6bb77,0x39a8b9a8,0x3444b5c2,
0xb9a839a8,0x3bfabbe2,0x39a8b9a8,0x2cb5b179,0x381db95f,0xbb503a0f,0xbadd39ed,0xb67c393a,0x30b2b564,0xbbe23bf1,0xbbea3b88,0x31792fd6,
0xb3c62a48,0xb9cb3b25,0xbbc33bfe,0x3984b732,0xb8c436d7,0xb30337e3,0xba6d3b3b,0x3bcebaf6,0xb4a53913,0x3be2ba4f,0x3ba8ba2f,0x3179b8ec,
0x378bae46,0x3984bb99,0x3b0ebbf6,0xb9cb3505,0x3ba8ba2f,0xb303b444,0x34a5b913,0xbbce3bb6,0x3b0ebbf6,0xbb77393a,0xb78b2e46,0xb5c23a0f,
0x2a48b8c4,0xbbfa3a8a,0xbbfe3a6d,0x2cb5389b,0xbb3b381d,0xafd639cb,0xb6d73add,0x3bf1b984,0xb9ed3bea,0x3b99b848,0x395fb0b2,0x3505bac2,
0x356433c6,0x37e3bb77,0x3b88bbc3,0xbaf635c2,0x323e3872,0x3b99bac2,0x3bd9baa7,0xb505b848,0x3bd9baa7,0xb7e3b5c2,0xb23eb872,0xbaf63b77,
0xb23eb872,0xba0f3be2,0xbbd93aa7,0x393a3179,0xbbd93aa7,0x3a4fa648,0x323e3872,0x38ecbbff,0xb6d7b81d,0xbac23af6,0xbb3b3add,0x384837e3,
0xb95f3bea,0x3b50acb5,0x39ed30b2,0x367cbbfa,0x3b88b3c6,0xb179ba4f,0x3564bbc3,0xbbe238ec,0xaa48ba6d,0xb9cb3b99,0xbbfe38c4,0x39843505,
0x3913378b,0x3984bb25,0x3a2fbb0e,0xb9cbb732,0x2e46bba8,0xbbce37e3,0xbbf634a5,0x33033af6,0xba2f3b0e,0x3b772cb5,0x3913378b,0x35c2bbfa,
0x3bf6b4a5,0xb89bb8ec,0x2e46bba8,0xba8a3a4f,0xba6db6d7,0xb7e33b50,0xb8c43b3b,0x3af6367c,0x381d39ed,0x393aba8a,0x3addb95f,0xba0fb89b,
0xb0b2bb88,0xba4f3984,0xbbea3564,0x38ec39cb,0xb3c63bfe,0x3b25b848,0x3bc32a48,0xb732bac2,0x3b64361f,0x3444bb77,0x361fbb64,0xbbb6b5c2,
0xbb64b61f,0xacb53be2,0xb61f3b64,0x3bfa3179,0x3b64361f,0xafd6bbff,0x361fbb64,0xbbf12648,0xbb64b61f,0x35053bce,0xb61f3b64,0x3b99b303,
0xbbeab564,0xa6483b99,0xb0b23b88,0x3bff3505,0x3bc3aa48,0xb848bbb6,0xb3c6bbfe,0xbac23444,0xba6d36d7,0x3b50393a,0x38c43b3b,0x367cba0f,
0x381db9ed,0xbbe2afd6,0xbaddb95f,0x31793bf1,0x3bf634a5,0xb303bbb6,0xae46bba8,0xbbceb444,0xb913378b,0x3b773a0f,0x3a2f3b0e,0x35c2b93a,
0xae46bba8,0xba8a2fd6,0xbbf6b4a5,0x389b3bf1,0x3a2f3b0e,0xa648bb25,0x3913b78b,0xbbffb732,0xbb88b3c6,0x37323bce,0x35643bc3,0x3b253303,
0x2a48ba6d,0xbbb6b67c,0xbbfeb8c4,0x34443b50,0x3b3b3add,0xacb5ba8a,0x36d7b81d,0xbbfab89b,0xb9ed30b2,0x3bf139cb,0x395f3bea,0x2fd6b984,
0x3aa7323e,0xb93abbe2,0xb872bbd9,0xba0fb179,0x38723bd9,0x38eca648,0x3aa7323e,0xba4fbbff,0xbaa7b23e,0x3b253bce,0x38723bd9,0x3732b303,
0xb872bbd9,0xb444367c,0xbaa7b23e,0x3bb63b50,0xb95fb0b2,0x3a8a3bf1,0x39ed3bea,0x389b2fd6,0xbb88bbc3,0xa6483732,0xb56433c6,0x3bff3b25,
0xaa48b8c4,0xbac2b7e3,0xbbfeba6d,0x38483af6,0x3b3b381d,0xbb50bbfa,0xb6d7badd,0xb67c2cb5,0x378b2e46,0xbb77bbfa,0xbb0ebbf6,0xb5c2acb5,
0x3ba83a2f,0xb89bba4f,0xb4a5b913,0xba8ab8ec,0x3b0e3bf6,0xa648b505,0x378b2e46,0xbbffbb99,0x34a53913,0x38483444,0x3ba83a2f,0xbac2bbb6,
0xb3c6aa48,0x3bf13bff,0x3bc33bfe,0x2fd62648,0xb8c4b6d7,0x3b993bce,0x3a6d3b3b,0x35053303,0xbaddb9ed,0x3af63b50,0x381d395f,0x37e3367c,
0xbbeabb88,0x3a0f3a8a,0x30b23564,0x393a389b,0x3c003c00,0x2fd62648,0,0x3bf13bff,0x3c003c00,0x35053303,0,0x3b993bce,
0x3c003c00,0x37e3367c,0,0x3af63b50,0x3c003c00,0x393a389b,0,0x3a0f3a8a,0xbbc3bbfe,0xb5c2acb5,0x33c62a48,0xbb77bbfa,
0xba6dbb3b,0xba8ab8ec,0x38c436d7,0xb89bba4f,0xb81db95f,0xbbffbb99,0x3add39ed,0xa648b505,0xb0b2b564,0xbac2bbb6,0x3bea3b88,0x38483444,
0x3b0e3bf6,0x389b2fd6,0xb78bae46,0x3a8a3bf1,0x34a53913,0x3bff3b25,0xbba8ba2f,0xa6483732,0xb78bae46,0x38483af6,0xbb0ebbf6,0xbac2b7e3,
0xbba8ba2f,0xb67c2cb5,0xb4a5b913,0xbb50bbfa,0xb9edbbea,0xba0fb179,0x395f30b2,0xb93abbe2,0x3564b3c6,0xba4fbbff,0x3b883bc3,0x38eca648,
0x3bfe3a6d,0x3732b303,0x2a4838c4,0x3b253bce,0x36d73add,0x3bb63b50,0xbb3bb81d,0xb444367c,0x38723bd9,0x3b253303,0xbaa7b23e,0x37323bce,
0xbaa7b23e,0x34443b50,0xb872bbd9,0xbbb6b67c,0xb872bbd9,0xbbfab89b,0x3aa7323e,0xacb5ba8a,0x3aa7323e,0x2fd6b984,0x38723bd9,0x3bf139cb,
0xb564bbc3,0xbbceb444,0x3b8833c6,0xb303bbb6,0x3bfe38c4,0x35c2b93a,0xaa483a6d,0x3b773a0f,0xb6d7381d,0x389b3bf1,0xbb3bbadd,0xba8a2fd6,
0xb95fbbea,0xbbffb732,0x39edb0b2,0xa648bb25,0x2e463ba8,0x3bff3505,0xbbf6b4a5,0xa6483b99,0xba2fbb0e,0xbac23444,0x3913b78b,0xb848bbb6,
0x3bf634a5,0x367cba0f,0x2e463ba8,0x3b50393a,0xb913378b,0x31793bf1,0xba2fbb0e,0xbbe2afd6,0x30b2bb88,0xbbb6b5c2,0x3bea3564,0x3444bb77,
0x33c63bfe,0x3bfa3179,0xbbc32a48,0xacb53be2,0xb8c4bb3b,0xbbf12648,0x3a6db6d7,0xafd6bbff,0x3add395f,0x3b99b303,0xb81d39ed,0x35053bce,
0xb61f3b64,0x3af6367c,0xbb64b61f,0xb7e33b50,0x361fbb64,0xba0fb89b,0x3b64361f,0x393aba8a,0xb61f3b64,0x38ec39cb,0xbb64b61f,0xba4f3984,
0x361fbb64,0xb732bac2,0x3b64361f,0x3b25b848,0x38c4bb3b,0xb9cbb732,0x3a6d36d7,0x3984bb25,0xbadd395f,0x33033af6,0xb81db9ed,0xbbce37e3,
0x3beab564,0x35c2bbfa,0x30b23b88,0x3b772cb5,0xbbc3aa48,0xba8a3a4f,0x33c6bbfe,0xb89bb8ec,0xba2f3b0e,0x384837e3,0xb913b78b,0xbac23af6,
0x3bf6b4a5,0x367cbbfa,0xae463ba8,0x3b50acb5,0xb913b78b,0xbbe238ec,0x3a2fbb0e,0xb179ba4f,0xae463ba8,0x39843505,0xbbf634a5,0xb9cb3b99,
0x3b3bbadd,0xb505b848,0x36d7381d,0x3b99bac2,0xb9edb0b2,0xbaf63b77,0x395fbbea,0xb7e3b5c2,0xb5643bc3,0x393a3179,0xbb8833c6,0xba0f3be2,
0x3bfeb8c4,0x38ecbbff,0x2a483a6d,0x3a4fa648,0xbbd93aa7,0x2cb5389b,0xb23eb872,0xbbfa3a8a,0x323e3872,0x3bf1b984,0xbbd93aa7,0xafd639cb,
0x3bd9baa7,0x3505bac2,0x323e3872,0x3b99b848,0xb23eb872,0xbaf635c2,0x3bd9baa7,0x37e3bb77,0x3bfeba6d,0x3179b8ec,0xaa4838c4,0x3be2ba4f,
0x36d7badd,0xb9cb3505,0x3b3bb81d,0x3984bb99,0xb95f30b2,0xbbce3bb6,0x39edbbea,0xb303b444,0xbb883bc3,0xb5c23a0f,0xb564b3c6,0xbb77393a,
0xbba83a2f,0xb67c393a,0x34a5b913,0xbb503a0f,0xbb0e3bf6,0x31792fd6,0xb78b2e46,0xbbe23bf1,0xb4a53913,0x3984b732,0xbba83a2f,0xb9cb3b25,
0x378bae46,0x3bcebaf6,0xbb0e3bf6,0xb30337e3,0x3addb9ed,0x38ecb984,0xb81d395f,0x3a4fb9cb,0x3beabb88,0x3732b848,0xb0b23564,0x3b25bac2,
0x3bc3bbfe,0x3444b5c2,0x33c6aa48,0x3bb6bb77,0x3a6dbb3b,0x2cb5b179,0x38c4b6d7,0x3bfabbe2,0xb9a839a8,0xba4f39cb,0x39a8b9a8,0xb8ec3984,
0xb9a839a8,0xbb253ac2,0x39a8b9a8,0xb7323848,0xb9a839a8,0xbbb63b77,0x39a8b9a8,0xb44435c2,0xb9a839a8,0xbbfa3be2,0x39a8b9a8,0xacb53179,
0x381db95f,0x3b50ba0f,0xbadd39ed,0x367cb93a,0x30b2b564,0x3be2bbf1,0xbbea3b88,0xb179afd6,0xb3c62a48,0x39cbbb25,0xbbc33bfe,0xb9843732,
0xb8c436d7,0x3303b7e3,0xba6d3b3b,0xbbce3af6,0xb4a53913,0xbbe23a4f,0x3ba8ba2f,0xb17938ec,0x378bae46,0xb9843b99,0x3b0ebbf6,0x39cbb505,
0x3ba8ba2f,0x33033444,0x34a5b913,0x3bcebbb6,0x3b0ebbf6,0x3b77b93a,0xb78b2e46,0x35c2ba0f,0x2a48b8c4,0x3bfaba8a,0xbbfe3a6d,0xacb5b89b,
0xbb3b381d,0x2fd6b9cb,0xb6d73add,0xbbf13984,0xb9ed3bea,0xbb993848,0x395fb0b2,0xb5053ac2,0x356433c6,0xb7e33b77,0x3b88bbc3,0x3af6b5c2,
0x323e3872,0xbb993ac2,0x3bd9baa7,0x35053848,0x3bd9baa7,0x37e335c2,0xb23eb872,0x3af6bb77,0xb23eb872,0x3a0fbbe2,0xbbd93aa7,0xb93ab179,
0xbbd93aa7,0xba4f2648,0x323e3872,0xb8ec3bff,0xb6d7b81d,0x3ac2baf6,0xbb3b3add,0xb848b7e3,0xb95f3bea,0xbb502cb5,0x39ed30b2,0xb67c3bfa,
0x3b88b3c6,0x31793a4f,0x3564bbc3,0x3be2b8ec,0xaa48ba6d,0x39cbbb99,0xbbfe38c4,0xb984b505,0x3913378b,0xb9843b25,0x3a2fbb0e,0x39cb3732,
0x2e46bba8,0x3bceb7e3,0xbbf634a5,0xb303baf6,0xba2f3b0e,0xbb77acb5,0x3913378b,0xb5c23bfa,0x3bf6b4a5,0x389b38ec,0x2e46bba8,0x3a8aba4f,
0xba6db6d7,0x37e3bb50,0xb8c43b3b,0xbaf6b67c,0x381d39ed,0xb93a3a8a,0x3addb95f,0x3a0f389b,0xb0b2bb88,0x3a4fb984,0xbbea3564,0xb8ecb9cb,
0xb3c63bfe,0xbb253848,0x3bc32a48,0x37323ac2,0x3b64361f,0xb4443b77,0x361fbb64,0x3bb635c2,0xbb64b61f,0x2cb5bbe2,0xb61f3b64,0xbbfab179,
0x3b64361f,0x2fd63bff,0x361fbb64,0x3bf1a648,0xbb64b61f,0xb505bbce,0xb61f3b64,0xbb993303,0xbbeab564,0x2648bb99,0xb0b23b88,0xbbffb505,
0x3bc3aa48,0x38483bb6,0xb3c6bbfe,0x3ac2b444,0xba6d36d7,0xbb50b93a,0x38c43b3b,0xb67c3a0f,0x381db9ed,0x3be22fd6,0xbaddb95f,0xb179bbf1,
0x3bf634a5,0x33033bb6,0xae46bba8,0x3bce3444,0xb913378b,0xbb77ba0f,0x3a2f3b0e,0xb5c2393a,0xae46bba8,0x3a8aafd6,0xbbf6b4a5,0xb89bbbf1,
0x3a2f3b0e,0x26483b25,0x3913b78b,0x3bff3732,0xbb88b3c6,0xb732bbce,0x35643bc3,0xbb25b303,0x2a48ba6d,0x3bb6367c,0xbbfeb8c4,0xb444bb50,
0x3b3b3add,0x2cb53a8a,0x36d7b81d,0x3bfa389b,0xb9ed30b2,0xbbf1b9cb,0x395f3bea,0xafd63984,0x3aa7323e,0x393a3be2,0xb872bbd9,0x3a0f3179,
0x38723bd9,0xb8ec2648,0x3aa7323e,0x3a4f3bff,0xbaa7b23e,0xbb25bbce,0x38723bd9,0xb7323303,0xb872bbd9,0x3444b67c,0xbaa7b23e,0xbbb6bb50,
0xb95fb0b2,0xba8abbf1,0x39ed3bea,0xb89bafd6,0xbb88bbc3,0x2648b732,0xb56433c6,0xbbffbb25,0xaa48b8c4,0x3ac237e3,0xbbfeba6d,0xb848baf6,
0x3b3b381d,0x3b503bfa,0xb6d7badd,0x367cacb5,0x378b2e46,0x3b773bfa,0xbb0ebbf6,0x35c22cb5,0x3ba83a2f,0x389b3a4f,0xb4a5b913,0x3a8a38ec,
0x3b0e3bf6,0x26483505,0x378b2e46,0x3bff3b99,0x34a53913,0xb848b444,0x3ba83a2f,0x3ac23bb6,0xb3c6aa48,0xbbf1bbff,0x3bc33bfe,0xafd6a648,
0xb8c4b6d7,0xbb99bbce,0x3a6d3b3b,0xb505b303,0xbaddb9ed,0xbaf6bb50,0x381d395f,0xb7e3b67c,0xbbeabb88,0xba0fba8a,0x30b23564,0xb93ab89b,
0x3c003c00,0xba4fb9cb,0,0xb8ecb984,0x3c003c00,0xbb25bac2,0,0xb732b848,0x3c003c00,0xbbb6bb77,0,0xb444b5c2,
0x3c003c00,0xbbfabbe2,0,0xacb5b179,0x33c62a48,0x367c393a,0x3bc33bfe,0xbb50ba0f,0x38c436d7,0xb1792fd6,0x3a6d3b3b,0xbbe2bbf1,
0x3add39ed,0xb984b732,0x381d395f,0xb9cbbb25,0x3bea3b88,0xbbcebaf6,0x30b23564,0xb303b7e3,0xbb0ebbf6,0x3be23a4f,0x378b2e46,0x317938ec,
0xb4a5b913,0x39843b99,0x3ba83a2f,0xb9cbb505,0x378b2e46,0xb3033444,0x3b0e3bf6,0xbbcebbb6,0x3ba83a2f,0xbb77b93a,0x34a53913,0xb5c2ba0f,
0xb95fb0b2,0x2cb5b89b,0xb9edbbea,0x3bfa3a8a,0xbb88bbc3,0x3bf13984,0x3564b3c6,0x2fd639cb,0xaa48b8c4,0x35053ac2,0x3bfe3a6d,0xbb99b848,
0x3b3b381d,0xbaf6b5c2,0x36d73add,0xb7e3bb77,0x38723bd9,0xbb99bac2,0xbaa7b23e,0x3505b848,0xbaa7b23e,0x37e3b5c2,0xb872bbd9,0x3af63b77,
0xb872bbd9,0x3a0f3be2,0x3aa7323e,0xb93a3179,0x3aa7323e,0xba4fa648,0x38723bd9,0xb8ecbbff,0x3b8833c6,0xb84837e3,0x35643bc3,0xbac2baf6,
0xaa483a6d,0xb67cbbfa,0xbbfeb8c4,0x3b502cb5,0xbb3bbadd,0x3be238ec,0x36d7b81d,0xb1793a4f,0x39edb0b2,0xb9843505,0x395f3bea,0xb9cbbb99,
0xae46bba8,0x39843b25,0x3bf634a5,0xb9cb3732,0x3a2f3b0e,0xbbceb7e3,0xb913378b,0x3303baf6,0xbbf6b4a5,0x3b77acb5,0xae46bba8,0x35c23bfa,
0x3913b78b,0xb89b38ec,0x3a2f3b0e,0xba8aba4f,0xbbeab564,0x3af6b67c,0x30b2bb88,0x37e33b50,0x3bc3aa48,0xba0f389b,0x33c63bfe,0xb93aba8a,
0xba6d36d7,0x38ecb9cb,0xb8c4bb3b,0x3a4f3984,0x381db9ed,0xb7323ac2,0x3add395f,0xbb25b848,0xb61f3b64,0xb444bb77,0xbb64b61f,0x3bb6b5c2,
0x361fbb64,0x2cb53be2,0x3b64361f,0xbbfa3179,0xb61f3b64,0x2fd6bbff,0xbb64b61f,0x3bf12648,0x361fbb64,0xb5053bce,0x3b64361f,0xbb99b303,
0x3a6d36d7,0xbbff3505,0xb8c43b3b,0xa648bb99,0xb81db9ed,0x3ac23444,0x3addb95f,0xb8483bb6,0x30b23b88,0xb67cba0f,0xbbea3564,0x3b50b93a,
0x33c6bbfe,0xb1793bf1,0x3bc32a48,0xbbe22fd6,0x3a2fbb0e,0xb3033bb6,0x3913378b,0xbbce3444,0xbbf634a5,0x3b77ba0f,0x2e46bba8,0x35c2393a,
0x3913378b,0xba8aafd6,0xba2f3b0e,0x389bbbf1,0x2e46bba8,0xa6483b25,0x3bf6b4a5,0xbbff3732,0xb6d7b81d,0x3b25b303,0x3b3bbadd,0xb7323bce,
0xb95f3bea,0x3444bb50,0xb9edb0b2,0x3bb6b67c,0x3b88b3c6,0xbbfa389b,0xb5643bc3,0x2cb5ba8a,0xaa48ba6d,0x2fd63984,0x3bfeb8c4,0xbbf139cb,
0xbbd93aa7,0x393abbe2,0xb23eb872,0x3a0fb179,0x323e3872,0xb8eca648,0xbbd93aa7,0x3a4fbbff,0x3bd9baa7,0xbb253bce,0x323e3872,0xb732b303,
0xb23eb872,0x3444367c,0x3bd9baa7,0xbbb63b50,0xaa4838c4,0xb89b2fd6,0xbbfe3a6d,0x3a8abbf1,0x3b3bb81d,0xbbff3b25,0xb6d73add,0xa648b732,
0x39edbbea,0xb8483af6,0x395fb0b2,0xbac237e3,0xb564b3c6,0x367c2cb5,0x3b88bbc3,0xbb503bfa,0x3ba8ba2f,0xbb773bfa,0xb4a53913,0xb5c22cb5,
0x3b0ebbf6,0xb89b3a4f,0x378bae46,0xba8a38ec,0x34a5b913,0xa6483505,0x3ba8ba2f,0xbbff3b99,0xb78b2e46,0x3848b444,0x3b0ebbf6,0xbac23bb6,
0x381db95f,0x2fd6a648,0x3addb9ed,0xbbf13bff,0x30b2b564,0x3505b303,0x3beabb88,0xbb993bce,0xb3c62a48,0x37e3b67c,0x3bc3bbfe,0xbaf63b50,
0xb8c436d7,0x393ab89b,0x3a6dbb3b,0xba0f3a8a,0xb9a839a8,0x3bf1bbff,0x39a8b9a8,0xafd62648,0xb9a839a8,0x3b99bbce,0x39a8b9a8,0xb5053303,
0xb9a839a8,0x3af6bb50,0x39a8b9a8,0xb7e3367c,0xb9a839a8,0x3a0fba8a,0x39a8b9a8,0xb93a389b,0xbadd39ed,0x35c2acb5,0xb81d395f,0x3b77bbfa,
0xbbea3b88,0x3a8ab8ec,0xb0b23564,0x389bba4f,0xbbc33bfe,0x3bffbb99,0x33c6aa48,0x2648b505,0xba6d3b3b,0x3ac2bbb6,0x38c4b6d7,0xb8483444,
0x34a5b913,0xba8a3bf1,0xbba83a2f,0x389bafd6,0xb78b2e46,0x26483732,0xbb0e3bf6,0x3bffbb25,0xbba83a2f,0x3ac2b7e3,0xb4a53913,0x3848baf6,
0xbb0e3bf6,0x3b50bbfa,0x378bae46,0xb67cacb5,0x3bfeba6d,0xba0f3179,0x2a48b8c4,0xb93a3be2,0x36d7badd,0xba4f3bff,0xbb3b381d,0x38ec2648,
0xb95f30b2,0x37323303,0xb9ed3bea,0x3b25bbce,0xbb883bc3,0x3bb6bb50,0x356433c6,0xb444b67c,0x323e3872,0x3732bbce,0x3bd9baa7,0xbb253303,
0x3bd9baa7,0xbbb6367c,0xb23eb872,0xb4443b50,0xb23eb872,0xacb53a8a,0xbbd93aa7,0x3bfab89b,0xbbd93aa7,0x3bf1b9cb,0x323e3872,0xafd6b984,
0xbb3b3add,0x3bceb444,0x36d7381d,0x3303bbb6,0x39ed30b2,0xb5c2b93a,0x395fbbea,0xbb773a0f,0x3564bbc3,0xb89b3bf1,0xbb8833c6,0x3a8a2fd6,
0xbbfe38c4,0x3bffb732,0x2a483a6d,0x2648bb25,0xb913b78b,0x26483b99,0xba2f3b0e,0x3bffb505,0xae463ba8,0x3848bbb6,0x3bf6b4a5,0xbac2b444,
0x3a2fbb0e,0xbb50393a,0xb913b78b,0x367c3a0f,0xbbf634a5,0x3be2afd6,0xae463ba8,0x3179bbf1,0x38c4bb3b,0xbbb635c2,0xba6db6d7,0x34443b77,
0xbadd395f,0x3bfab179,0x381d39ed,0xacb5bbe2,0x3beab564,0xbbf1a648,0xb0b2bb88,0xafd63bff,0xbbc3aa48,0x3b993303,0xb3c63bfe,0x3505bbce,
0x3b64361f,0xb7e3bb50,0x361fbb64,0xbaf6367c,0xbb64b61f,0x393a3a8a,0xb61f3b64,0x3a0fb89b,0x3b64361f,0xba4fb984,0x361fbb64,0xb8ec39cb,
0xbb64b61f,0x3b253848,0xb61f3b64,0x3732bac2,0xb0b23b88,0x39cbb732,0x3bea3564,0xb984bb25,0xb3c6bbfe,0xb3033af6,0xbbc32a48,0x3bce37e3,
0x38c43b3b,0xb5c2bbfa,0x3a6db6d7,0xbb772cb5,0xbaddb95f,0x3a8a3a4f,0xb81d39ed,0x389bb8ec,0xbbf6b4a5,0x3ac23af6,0x2e463ba8,0x3848b7e3,
0x3913b78b,0xbb50acb5,0xba2fbb0e,0x367c3bfa,0x2e463ba8,0x3179ba4f,0x3bf634a5,0xbbe2b8ec,0xba2fbb0e,0x39cb3b99,0xb913378b,0x3984b505,
0xb564bbc3,0xb5053848,0xbb88b3c6,0x3b993ac2,0x3bfe38c4,0xbaf6bb77,0x2a48ba6d,0xb7e335c2,0xb6d7381d,0x393ab179,0x3b3b3add,0xba0fbbe2,
0xb95fbbea,0x38ec3bff,0xb9ed30b2,0x3a4f2648,0x3aa7323e,0xbbfaba8a,0xb872bbd9,0xacb5389b,0x38723bd9,0xafd6b9cb,0x3aa7323e,0xbbf1b984,
0xbaa7b23e,0x3b993848,0x38723bd9,0xb505bac2,0xb872bbd9,0x37e33b77,0xbaa7b23e,0x3af635c2,0x39ed3bea,0xb179b8ec,0x395f30b2,0xbbe2ba4f,
0xb56433c6,0x39cb3505,0x3b883bc3,0xb984bb99,0xbbfeba6d,0x3bce3bb6,0x2a4838c4,0x3303b444,0xb6d7badd,0x35c23a0f,0xbb3bb81d,0x3b77393a,
0xb78bae46,0x3b503a0f,0x3b0e3bf6,0xb67cb93a,0xbba8ba2f,0x3be23bf1,0x34a53913,0x3179afd6,0xbb0ebbf6,0x39cb3b25,0xb78bae46,0x39843732,
0xb4a5b913,0x330337e3,0xbba8ba2f,0x3bce3af6,0xbbc3bbfe,0x38ec3984,0xb3c6aa48,0x3a4f39cb,0xba6dbb3b,0x37323848,0xb8c4b6d7,0x3b253ac2,
0xb81db95f,0x344435c2,0xbaddb9ed,0x3bb63b77,0xb0b2b564,0x2cb53179,0xbbeabb88,0x3bfa3be2,0x3c003c00,0x3a4f39cb,0,0x38ec3984,
0x3c003c00,0x3b253ac2,0,0x37323848,0x3c003c00,0x3bb63b77,0,0x344435c2,0x3c003c00,0x3bfa3be2,0,0x2cb53179,
0x33c62a48,0xb67cb93a,0x3bc33bfe,0x3b503a0f,0x38c436d7,0x3179afd6,0x3a6d3b3b,0x3be23bf1,0x3add39ed,0x39843732,0x381d395f,0x39cb3b25,
0x3bea3b88,0x3bce3af6,0x30b23564,0x330337e3,0xbb0ebbf6,0xbbe2ba4f,0x378b2e46,0xb179b8ec,0xb4a5b913,0xb984bb99,0x3ba83a2f,0x39cb3505,
0x378b2e46,0x3303b444,0x3b0e3bf6,0x3bce3bb6,0x3ba83a2f,0x3b77393a,0x34a53913,0x35c23a0f,0xb95fb0b2,0xacb5389b,0xb9edbbea,0xbbfaba8a,
0xbb88bbc3,0xbbf1b984,0x3564b3c6,0xafd6b9cb,0xaa48b8c4,0xb505bac2,0x3bfe3a6d,0x3b993848,0x3b3b381d,0x3af635c2,0x36d73add,0x37e33b77,
0x38723bd9,0x3b993ac2,0xbaa7b23e,0xb5053848,0xbaa7b23e,0xb7e335c2,0xb872bbd9,0xbaf6bb77,0xb872bbd9,0xba0fbbe2,0x3aa7323e,0x393ab179,
0x3aa7323e,0x3a4f2648,0x38723bd9,0x38ec3bff,0x3b8833c6,0x3848b7e3,0x35643bc3,0x3ac23af6,0xaa483a6d,0x367c3bfa,0xbbfeb8c4,0xbb50acb5,
0xbb3bbadd,0xbbe2b8ec,0x36d7b81d,0x3179ba4f,0x39edb0b2,0x3984b505,0x395f3bea,0x39cb3b99,0xae46bba8,0xb984bb25,0x3bf634a5,0x39cbb732,
0x3a2f3b0e,0x3bce37e3,0xb913378b,0xb3033af6,0xbbf6b4a5,0xbb772cb5,0xae46bba8,0xb5c2bbfa,0x3913b78b,0x389bb8ec,0x3a2f3b0e,0x3a8a3a4f,
0xbbeab564,0xbaf6367c,0x30b2bb88,0xb7e3bb50,0x3bc3aa48,0x3a0fb89b,0x33c63bfe,0x393a3a8a,0xba6d36d7,0xb8ec39cb,0xb8c4bb3b,0xba4fb984,
0x381db9ed,0x3732bac2,0x3add395f,0x3b253848,0xb61f3b64,0x34443b77,0xbb64b61f,0xbbb635c2,0x361fbb64,0xacb5bbe2,0x3b64361f,0x3bfab179,
0xb61f3b64,0xafd63bff,0xbb64b61f,0xbbf1a648,0x361fbb64,0x3505bbce,0x3b64361f,0x3b993303,0x3a6d36d7,0x3bffb505,0xb8c43b3b,0x26483b99,
0xb81db9ed,0xbac2b444,0x3addb95f,0x3848bbb6,0x30b23b88,0x367c3a0f,0xbbea3564,0xbb50393a,0x33c6bbfe,0x3179bbf1,0x3bc32a48,0x3be2afd6,
0x3a2fbb0e,0x3303bbb6,0x3913378b,0x3bceb444,0xbbf634a5,0xbb773a0f,0x2e46bba8,0xb5c2b93a,0x3913378b,0x3a8a2fd6,0xba2f3b0e,0xb89b3bf1,
0x2e46bba8,0x2648bb25,0x3bf6b4a5,0x3bffb732,0xb6d7b81d,0xbb253303,0x3b3bbadd,0x3732bbce,0xb95f3bea,0xb4443b50,0xb9edb0b2,0xbbb6367c,
0x3b88b3c6,0x3bfab89b,0xb5643bc3,0xacb53a8a,0xaa48ba6d,0xafd6b984,0x3bfeb8c4,0x3bf1b9cb,0xbbd93aa7,0xb93a3be2,0xb23eb872,0xba0f3179,
0x323e3872,0x38ec2648,0xbbd93aa7,0xba4f3bff,0x3bd9baa7,0x3b25bbce,0x323e3872,0x37323303,0xb23eb872,0xb444b67c,0x3bd9baa7,0x3bb6bb50,
0xaa4838c4,0x389bafd6,0xbbfe3a6d,0xba8a3bf1,0x3b3bb81d,0x3bffbb25,0xb6d73add,0x26483732,0x39edbbea,0x3848baf6,0x395fb0b2,0x3ac2b7e3,
0xb564b3c6,0xb67cacb5,0x3b88bbc3,0x3b50bbfa,0x3ba8ba2f,0x3b77bbfa,0xb4a53913,0x35c2acb5,0x3b0ebbf6,0x389bba4f,0x378bae46,0x3a8ab8ec,
0x34a5b913,0x2648b505,0x3ba8ba2f,0x3bffbb99,0xb78b2e46,0xb8483444,0x3b0ebbf6,0x3ac2bbb6,0x381db95f,0xafd62648,0x3addb9ed,0x3bf1bbff,
0x30b2b564,0xb5053303,0x3beabb88,0x3b99bbce,0xb3c62a48,0xb7e3367c,0x3bc3bbfe,0x3af6bb50,0xb8c436d7,0xb93a389b,0x3a6dbb3b,0x3a0fba8a,
0xb9a839a8,0xbbf13bff,0x39a8b9a8,0x2fd6a648,0xb9a839a8,0xbb993bce,0x39a8b9a8,0x3505b303,0xb9a839a8,0xbaf63b50,0x39a8b9a8,0x37e3b67c,
0xb9a839a8,0xba0f3a8a,0x39a8b9a8,0x393ab89b,0xbadd39ed,0xb5c22cb5,0xb81d395f,0xbb773bfa,0xbbea3b88,0xba8a38ec,0xb0b23564,0xb89b3a4f,
0xbbc33bfe,0xbbff3b99,0x33c6aa48,0xa6483505,0xba6d3b3b,0xbac23bb6,0x38c4b6d7,0x3848b444,0x34a5b913,0x3a8abbf1,0xbba83a2f,0xb89b2fd6,
0xb78b2e46,0xa648b732,0xbb0e3bf6,0xbbff3b25,0xbba83a2f,0xbac237e3,0xb4a53913,0xb8483af6,0xbb0e3bf6,0xbb503bfa,0x378bae46,0x367c2cb5,
0x3bfeba6d,0x3a0fb179,0x2a48b8c4,0x393abbe2,0x36d7badd,0x3a4fbbff,0xbb3b381d,0xb8eca648,0xb95f30b2,0xb732b303,0xb9ed3bea,0xbb253bce,
0xbb883bc3,0xbbb63b50,0x356433c6,0x3444367c,0x323e3872,0xb7323bce,0x3bd9baa7,0x3b25b303,0x3bd9baa7,0x3bb6b67c,0xb23eb872,0x3444bb50,
0xb23eb872,0x2cb5ba8a,0xbbd93aa7,0xbbfa389b,0xbbd93aa7,0xbbf139cb,0x323e3872,0x2fd63984,0xbb3b3add,0xbbce3444,0x36d7381d,0xb3033bb6,
0x39ed30b2,0x35c2393a,0x395fbbea,0x3b77ba0f,0x3564bbc3,0x389bbbf1,0xbb8833c6,0xba8aafd6,0xbbfe38c4,0xbbff3732,0x2a483a6d,0xa6483b25,
0xb913b78b,0xa648bb99,0xba2f3b0e,0xbbff3505,0xae463ba8,0xb8483bb6,0x3bf6b4a5,0x3ac23444,0x3a2fbb0e,0x3b50b93a,0xb913b78b,0xb67cba0f,
0xbbf634a5,0xbbe22fd6,0xae463ba8,0xb1793bf1,0x38c4bb3b,0x3bb6b5c2,0xba6db6d7,0xb444bb77,0xbadd395f,0xbbfa3179,0x381d39ed,0x2cb53be2,
0x3beab564,0x3bf12648,0xb0b2bb88,0x2fd6bbff,0xbbc3aa48,0xbb99b303,0xb3c63bfe,0xb5053bce,0x3b64361f,0x37e33b50,0x361fbb64,0x3af6b67c,
0xbb64b61f,0xb93aba8a,0xb61f3b64,0xba0f389b,0x3b64361f,0x3a4f3984,0x361fbb64,0x38ecb9cb,0xbb64b61f,0xbb25b848,0xb61f3b64,0xb7323ac2,
0xb0b23b88,0xb9cb3732,0x3bea3564,0x39843b25,0xb3c6bbfe,0x3303baf6,0xbbc32a48,0xbbceb7e3,0x38c43b3b,0x35c23bfa,0x3a6db6d7,0x3b77acb5,
0xbaddb95f,0xba8aba4f,0xb81d39ed,0xb89b38ec,0xbbf6b4a5,0xbac2baf6,0x2e463ba8,0xb84837e3,0x3913b78b,0x3b502cb5,0xba2fbb0e,0xb67cbbfa,
0x2e463ba8,0xb1793a4f,0x3bf634a5,0x3be238ec,0xba2fbb0e,0xb9cbbb99,0xb913378b,0xb9843505,0xb564bbc3,0x3505b848,0xbb88b3c6,0xbb99bac2,
0x3bfe38c4,0x3af63b77,0x2a48ba6d,0x37e3b5c2,0xb6d7381d,0xb93a3179,0x3b3b3add,0x3a0f3be2,0xb95fbbea,0xb8ecbbff,0xb9ed30b2,0xba4fa648,
0x3aa7323e,0x3bfa3a8a,0xb872bbd9,0x2cb5b89b,0x38723bd9,0x2fd639cb,0x3aa7323e,0x3bf13984,0xbaa7b23e,0xbb99b848,0x38723bd9,0x35053ac2,
0xb872bbd9,0xb7e3bb77,0xbaa7b23e,0xbaf6b5c2,0x39ed3bea,0x317938ec,0x395f30b2,0x3be23a4f,0xb56433c6,0xb9cbb505,0x3b883bc3,0x39843b99,
0xbbfeba6d,0xbbcebbb6,0x2a4838c4,0xb3033444,0xb6d7badd,0xb5c2ba0f,0xbb3bb81d,0xbb77b93a,0xb78bae46,0xbb50ba0f,0x3b0e3bf6,0x367c393a,
0xbba8ba2f,0xbbe2bbf1,0x34a53913,0xb1792fd6,0xbb0ebbf6,0xb9cbbb25,0xb78bae46,0xb984b732,0xb4a5b913,0xb303b7e3,0xbba8ba2f,0xbbcebaf6,
0xbbc3bbfe,0xb8ecb984,0xb3c6aa48,0xba4fb9cb,0xba6dbb3b,0xb732b848,0xb8c4b6d7,0xbb25bac2,0xb81db95f,0xb444b5c2,0xbaddb9ed,0xbbb6bb77,
0xb0b2b564,0xacb5b179,0xbbeabb88,0xbbfabbe2,0x3c003c00,0x96480000,0x3c003c00,0xa311a248,0x3c003c00,0x9cb69a48,0x3c003c00,0xa452a3db,
0x3c003c00,0x9fdb9e48,0x3c003c00,0xa51ba4b6,0x3c003c00,0xa17fa0b6,0x3bff3c00,0xa5e4a57f,0x3c003c00,0x9fdb0000,0x3bfb3bfc,0xac6aabd9,
0x3bff3c00,0xa5e4a3db,0x3bf93bfa,0xad65ace7,0x3bfe3bff,0xa8e8a7da,0x3bf63bf7,0xae5fade2,0x3bfd3bfe,0xaadea9e3,0x3bf23bf4,0xaf59aedc,
0x3c003c00,0xa3110000,0x3bf03bf4,0xafefaf0e,0x3bfe3bff,0xa94da711,0x3be83bed,0xb0d7b067,0x3bfb3bfd,0xac6aab11,0x3bdf3be4,0xb1b6b147,
0x3bf63bf9,0xae2dad4c,0x3bd43bda,0xb294b226,0x3c003c00,0xa51b0000,0x3bdf3be6,0xb1b6b115,0x3bfc3bfe,0xaba7a91b,0x3bcf3bd7,0xb2f7b257,
0x3bf63bf9,0xae5fad1a,0x3bbc3bc6,0xb41ab396,0x3bec3bf1,0xb074afa4,0x3ba53bb1,0xb4b7b469,0x3bff3c00,0xa6ad0000,0x3bc83bd4,0xb371b2a1,
0x3bfa3bfd,0xad00aaac,0x3bac3bbb,0xb487b420,0x3bef3bf5,0xb029aeaa,0x3b8b3b9d,0xb552b4ed,0x3bde3be7,0xb1cfb0fd,0x3b653b79,0xb61ab5b6,
0x3bff3c00,0xa81f0000,0x3bab3bbc,0xb493b414,0x3bf63bfc,0xae2dac1f,0x3b813b97,0xb58db511,0x3be53bef,0xb122b01d,0x3b4f3b69,0xb682b608,
0x3bcc3bda,0xb328b226,0x3b163b33,0xb76fb6f9,0x3bfe3c00,0xa8e80000,0x3b873ba0,0xb56ab4d5,0x3bf23bfa,0xaf59ace7,0x3b4c3b6b,0xb68db5fd,
0x3bda3be8,0xb219b0e4,0x3b073b2b,0xb7a6b71b,0x3bb73bca,0xb43eb34c,0x3ab63ae0,0xb85ab817,0x3bfe3c00,0xa9b10000,0x3b5e3b80,0xb63cb593,
0x3bee3bf8,0xb042adb0,0x3b103b39,0xb785b6e3,0x3bce3be0,0xb30fb1aa,0x3ab33ae3,0xb85fb812,0x3b9e3bb7,0xb4e7b438,0x3a493a7f,0xb8f3b8ab,
0x3bfd3c00,0xaa7a0000,0x3b2f3b5a,0xb70ab64e,0x3be83bf6,0xb0d7ae78,0x3acb3aff,0xb83ab7c2,0x3bbf3bd6,0xb402b26f,0x3a543a92,0xb8e5b891,
0x3b813ba2,0xb58db4c9,0x39cd3a13,0xb982b935,0x3bfd3c00,0xab430000,0x3afb3b30,0xb7d2b705,0x3be23bf3,0xb16caf40,0x3a7e3abf,0xb8adb84d,
0x3bae3bcb,0xb47bb334,0x39eb3a37,0xb962b909,0x3b603b8a,0xb631b558,0x3946399b,0xba04b9b5,0x3bfc3c00,0xac060000,0x3ac13b02,0xb84ab7b7,
0x3bdc3bf0,0xb201b004,0x3a293a78,0xb91bb8b5,0x3b9c3bc0,0xb4f3b3f7,0x397939d4,0xb9d6b97b,0x3b3d3b70,0xb6d2b5e5,0x38b23918,0xba7aba2b,
0x3bfb3c00,0xac6a0000,0x3a813ad0,0xb8a8b832,0x3bd43bed,0xb294b067,0x39cd3a2b,0xb982b918,0x3b873bb2,0xb56ab45d,0x38fd3969,0xba41b9e5,
0x3b163b53,0xb76fb670,0x3815388c,0xbae1ba95,0x3bfa3c00,0xacce0000,0x3a3d3a99,0xb902b887,0x3bcc3be9,0xb328b0cb,0x396b39d8,0xb9e3b976,
0x3b713ba4,0xb5dfb4bd,0x387a38f6,0xbaa2ba47,0x3aeb3b33,0xb805b6f9,0x36dd37ee,0xbb3abaf3,0x3bf93c00,0xad330000,0x39f43a5e,0xb958b8d8,
0x3bc33be5,0xb3bab12e,0x39023980,0xba3db9d0,0x3b593b95,0xb654b51d,0x37dd387c,0xbaf7baa0,0x3abd3b11,0xb850b780,0x358136b5,0xbb83bb43,
0x3bf83c00,0xad970000,0x39a63a1f,0xb9aab927,0x3bba3be1,0xb426b191,0x38943922,0xba90ba23,0x3b3f3b84,0xb6c6b57c,0x36bb37f9,0xbb42baf0,
0x3a8c3aed,0xb899b802,0x341a3570,0xbbbcbb86,0x3bf73c00,0xadfb0000,0x395439dc,0xb9f8b972,0x3bb03bdc,0xb46fb1f4,0x382038bf,0xbadbba71,
0x3b243b72,0xb737b5da,0x358d36ee,0xbb81bb36,0x3a583ac6,0xb8e0b842,0x31533420,0xbbe3bbbb,0x3bf63c00,0xae5f0000,0x38fd3996,0xba41b9ba,
0x3ba53bd7,0xb4b7b257,0x374e3858,0xbb1ebab8,0x3b073b5f,0xb7a6b637,0x345735da,0xbbb3bb72,0x3a213a9c,0xb924b881,0x2cce3191,0xbbfabbe1,
0x3bf53c00,0xaec30000,0x38a3394d,0xba85b9fe,0x3b9a3bd2,0xb4ffb2b9,0x365437d8,0xbb59baf9,0x3ae83b4b,0xb80ab693,0x323234bd,0xbbd9bba4,
0x39e73a71,0xb966b8bf,0xa4522db0,0xbc00bbf8,0x3bf33c00,0xaf270000,0x38453900,0xbac4ba3f,0x3b8e3bcd,0xb546b31b,0x355236f9,0xbb8bbb33,
0x3ac73b36,0xb840b6ee,0x2f593334,0xbbf2bbcb,0x39aa3a43,0xb9a6b8fb,0xaef51a48,0xbbf4bc00,0x3bf23c00,0xaf8b0000,0x37c838b0,0xbafeba7c,
0x3b813bc7,0xb58db37d,0x344b3614,0xbbb5bb67,0x3aa53b20,0xb874b748,0x288430e4,0xbbffbbe8,0x396b3a13,0xb9e3b935,0xb263ad4c,0xbbd7bbf9,
0x3bf03c00,0xafef0000,0x36ff385d,0xbb32bab5,0x3b733bc1,0xb5d4b3df,0x327c3529,0xbbd6bb93,0x3a813b08,0xb8a8b7a1,0xa9b12d1a,0xbbfebbf9,
0x392939e1,0xba1db96d,0xb49fb160,0xbba9bbe3,0x3bef3c00,0xb0290000,0x36313807,0xbb60bae9,0x3b653bbb,0xb61ab420,0x305b3438,0xbbedbbb7,
0x3a5c3af0,0xb8dbb7f9,0xafef1e48,0xbbf0bc00,0x38e539ad,0xba54b9a4,0xb602b408,0xbb6abbbe,0x3bed3c00,0xb05b0000,0x355e375e,0xbb89bb1a,
0x3b573bb4,0xb65fb451,0x2c6a3288,0xbbfbbbd5,0x3a353ad6,0xb90cb828,0xb27cac51,0xbbd6bbfb,0x389e3976,0xba89b9d8,0xb759b558,0xbb1bbb8a,
0x3beb3c00,0xb08d0000,0x348736aa,0xbbacbb46,0x3b473bad,0xb6a4b481,0x16483099,0xbc00bbeb,0x3a0d3abc,0xb93cb852,0xb47bb080,0xbbaebbec,
0x3855393e,0xbababa0b,0xb850b69e,0xbabdbb49,0x3be93c00,0xb0be0000,0x335935f1,0xbbc9bb6e,0x3b373ba6,0xb6e8b4b1,0xac382d4c,0xbbfcbbf9,
0x39e33aa0,0xb96bb87c,0xb5b1b2d2,0xbb7abbd1,0x380a3905,0xbae8ba3b,0xb8eab7d8,0xba50baf9,0x3be73c00,0xb0f00000,0x319e3534,0xbbe0bb91,
0x3b273b9e,0xb72cb4e1,0xb042257f,0xbbeebc00,0x39b83a83,0xb999b8a6,0xb6ddb48d,0xbb3abbab,0x377a38c9,0xbb13ba69,0xb979b881,0xb9d6ba9c,
0x3be53c00,0xb1220000,0x2fbd3475,0xbbf1bbaf,0x3b163b97,0xb76fb511,0xb263a91b,0xbbd7bbfe,0x398b3a65,0xb9c5b8ce,0xb7feb5ab,0xbaeebb7b,
0x36dd388c,0xbb3aba95,0xb9fcb90e,0xb94fba33,0x3be33c00,0xb1530000,0x2c383365,0xbbfcbbc9,0x3b043b8f,0xb7b2b540,0xb43eae78,0xbbb7bbf6,
0x395d3a47,0xb9f0b8f6,0xb889b6c1,0xba97bb41,0x363c384d,0xbb5ebabf,0xba73b992,0xb8bcb9be,0x3be13c00,0xb1850000,0x217f31db,0xbc00bbdd,
0x3af13b86,0xb7f3b570,0xb546b12e,0xbb8ebbe5,0x392e3a27,0xba19b91d,0xb90cb7cd,0xba35bafc,0x3599380d,0xbb7fbae6,0xbadbba0b,0xb820b93e,
0x3bdf3c00,0xb1b60000,0xa9b1304e,0xbbfebbed,0x3ade3b7d,0xb81ab59f,0xb648b31b,0xbb5cbbcd,0x38fd3a07,0xba41b943,0xb986b867,0xb9c9baae,
0x34f33796,0xbb9cbb0b,0xbb35ba78,0xb6f4b8b5,0x3bdd3c00,0xb1e80000,0xae5f2d7e,0xbbf6bbf8,0x3acb3b74,0xb83ab5ce,0xb742b481,0xbb21bbad,
0x38cc39e5,0xba67b969,0xb9f8b8e2,0xb954ba56,0x344b3710,0xbbb5bb2e,0xbb7fbad9,0xb599b822,0x3bda3c00,0xb2190000,0xb0f028b6,0xbbe7bbff,
0x3ab63b6b,0xb85ab5fd,0xb81ab570,0xbadebb86,0x389939c3,0xba8cb98d,0xba60b956,0xb8d6b9f6,0x33403687,0xbbcbbb4e,0xbbb8bb2e,0xb432b710,
0x3bff3bff,0xa6ada648,0x3bfe3bff,0xa8e8a8b6,0x3bff3bff,0xa776a711,0x3bfe3bfe,0xa94da91b,0x3bff3bff,0xa81fa7da,0x3bfe3bfe,0xa9b1a97f,
0x3bff3bff,0xa884a852,0x3bfe3bfe,0xaa16a9e3,0x3bef3bf1,0xb029afd6,0x3bda3bdd,0xb219b1db,0x3bea3bed,0xb0a6b067,0x3bd43bd7,0xb294b257,
0x3be53be8,0xb122b0e4,0x3bce3bd1,0xb30fb2d2,0x3be03be3,0xb19eb160,0x3bc63bca,0xb389b34c,0x3bc83bce,0xb371b303,0x3b873b91,0xb56ab534,
0x3bba3bc1,0xb426b3df,0x3b733b7d,0xb5d4b59f,0x3bab3bb2,0xb493b45d,0x3b5e3b69,0xb63cb608,0x3b9a3ba2,0xb4ffb4c9,0x3b473b53,0xb6a4b670,
0x3b8b3b99,0xb552b505,0x3b073b1a,0xb7a6b75e,0x3b6f3b7d,0xb5ebb59f,0x3ade3af3,0xb81ab7ee,0x3b4f3b5f,0xb682b637,0x3ab33ac9,0xb85fb83d,
0x3b2c3b3e,0xb715b6cc,0x3a853a9c,0xb8a3b881,0x3b3a3b50,0xb6ddb67c,0x3a5c3a7c,0xb8dbb8b0,0x3b0a3b22,0xb79bb73d,0x3a193a3b,0xb92eb905,
0x3ad53af0,0xb82ab7f9,0x39d239f6,0xb97db956,0x3a9b3ab8,0xb884b858,0x398639ad,0xb9c9b9a4,0x3ad53af6,0xb82ab7e3,0x398b39ba,0xb9c5b996,
0x3a8c3ab1,0xb899b862,0x3929395b,0xba1db9f2,0x3a3d3a65,0xb902b8ce,0x38c138f6,0xba6fba47,0x39e73a13,0xb966b935,0x3855388c,0xbababa95,
0x3a5c3a8a,0xb8dbb89b,0x389938d8,0xba8cba5e,0x39f83a2b,0xb954b918,0x38153858,0xbae1bab8,0x398b39c3,0xb9c5b98d,0x371537a1,0xbb2cbb08,
0x39163951,0xba2db9fa,0x35f73687,0xbb6cbb4e,0x39d23a0f,0xb97db93a,0x371537b7,0xbb2cbb02,0x394f3992,0xb9fcb9be,0x35c83670,0xbb76bb53,
0x38c13909,0xba6fba37,0x346f351d,0xbbb0bb95,0x382a3877,0xbad5baa3,0x3219337d,0xbbdabbc7,0x39373984,0xba11b9cb,0x34cf3593,0xbba1bb80,
0x389438e7,0xba90ba52,0x327c3408,0xbbd6bbbe,0x37c8383d,0xbafebac9,0x2e9130e4,0xbbf5bbe8,0x36543710,0xbb59bb2e,0x16482aac,0xbc00bbfd,
0x388e38ec,0xba93ba4f,0x30d732a1,0xbbe8bbd4,0x3790382d,0xbb0dbad3,0x28e82e14,0xbbfebbf7,0x35eb36c1,0xbb6fbb41,0xaccea4b6,0xbbfabc00,
0x34323511,0xbbb8bb97,0xb201b036,0xbbdcbbee,0x37b23848,0xbb04bac2,0x96482bd9,0xbc00bbfc,0x35df36cc,0xbb71bb3e,0xb010ac1f,0xbbefbbfc,
0x33eb34ed,0xbbc0bb9d,0xb402b20d,0xbbbfbbdb,0x2fef31f4,0xbbf0bbdc,0xb5ebb4f9,0xbb6fbb9b,0x36313732,0xbb60bb25,0xb0f0ad7e,0xbbe7bbf8,
0x341a3529,0xbbbcbb93,0xb49fb31b,0xbba9bbcd,0x2fbd320d,0xbbf1bbdb,0xb6afb5ab,0xbb45bb7b,0xa4522aac,0xbc00bbfd,0xb850b7ac,0xbabdbb05,
0x349f35c2,0xbba9bb77,0xb4dbb365,0xbb9fbbc9,0x308d32ea,0xbbebbbd0,0xb715b5fd,0xbb2cbb6b,0x9fdb2c51,0xbc00bbfb,0xb894b812,0xba90bae3,
0xb109ad4c,0xbbe6bbf9,0xb982b90e,0xb9cdba33,0x32013444,0xbbdcbbb6,0xb721b5f1,0xbb2abb6e,0x26ad2edc,0xbbffbbf4,0xb8adb822,0xba7ebad9,
0xb05bab11,0xbbedbbfd,0xb9aab930,0xb9a6ba17,0xb4b7b2ea,0xbba5bbd0,0xba81ba1b,0xb8a8b92b,0x2d653179,0xbbf9bbe2,0xb89eb807,0xba89bae9,
0xadc99a48,0xbbf8bc00,0xb9afb92b,0xb9a1ba1b,0xb432b1aa,0xbbb8bbe0,0xba93ba27,0xb88eb91d,0xb6d2b587,0xbb3dbb82,0xbb45baf3,0xb6afb7ee,
0xa51b2cb5,0xbc00bbfa,0xb990b900,0xb9c0ba3f,0xb294af40,0xbbd4bbf3,0xba89ba13,0xb89eb935,0xb625b4bd,0xbb63bba4,0xbb47baf0,0xb6a4b7f9,
0xb865b780,0xbab0bb11,0xbbc5bb8f,0xb3a2b540,0xafefa648,0xbbf0bbff,0xba60b9dc,0xb8d6b972,0xb517b31b,0xbb96bbcd,0xbb35bad3,0xb6f4b82d,
0xb7feb693,0xbaeebb4b,0xbbc0bb84,0xb3ebb57c,0xb94ab8ab,0xba00ba7f,0xbbfdbbe9,0xaa7ab0cb,0xb340afd6,0xbbcbbbf1,0xbb0aba99,0xb79bb887,
0xb6d2b540,0xbb3dbb8f,0xbbaebb67,0xb47bb614,0xb8dbb828,0xba5cbad6,0xbbfbbbe0,0xac9cb1aa,0xba15b980,0xb933b9d0,0xbbecbbff,0x30742852,
0xb53ab303,0xbb90bbce,0xbb89bb30,0xb55eb705,0xb83ab6e3,0xbacbbb39,0xbbf2bbca,0xaf8bb34c,0xb9a1b8f6,0xb9afba47,0xbbf5bc00,0x2ec39e48,
0xbac1ba3b,0xb84ab905,0xbb92bbd0,0x352f32ea,0xb6c6b505,0xbb3fbb99,0xbbdcbba0,0xb201b4d5,0xb8fdb838,0xba41bacc,0xbbfebbfb,0x2a16ac83,
0xba50b9b1,0xb8eab99f,0xbbaebbe4,0x347b3147,0xbb4abad9,0xb699b822,0xbaf1bb5d,0x37f33642,0xb820b67c,0xbadbbb50,0xbbffbbe6,0xa884b115,
0xb9afb8f1,0xb9a1ba4b,0xbbd2bbf8,0x32c62db0,0xbae5ba56,0xb80fb8e2,0xbb2abb8c,0x3721354c,0xbbaebb58,0xb47bb659,0xba11baaa,0x3937386d,
0xb8d1b7e3,0xba64baf6,0xbbf2bc00,0x2f8ba248,0xba4db99b,0xb8eeb9b5,0xbb6fbbc1,0x35eb33df,0xbb5cbae3,0xb648b812,0xba6bbafc,0x38c737cd,
0xbbebbbb4,0xb08db451,0xb8f8b9be,0x3a453992,0xb974b89b,0xb9daba8a,0xbbb5bbed,0x344b304e,0xbad5ba33,0xb82ab90e,0xbad8bb58,0x38253659,
0xbbb3bb55,0xb457b665,0xb979ba37,0x39d63909,0xbc00bbed,0x9648b067,0xb764b8a0,0x3b183a87,0xba09b93a,0xb941ba0f,0xbb4abbaf,0x36993475,
0xbb45bab8,0xb6afb858,0xba11babf,0x3937384d,0xbbeabbab,0xb0a6b48d,0xb85ab943,0x3ab63a07,0xbbecbc00,0x30749a48,0xb493b6b5,0x3bab3b43,
0xba8cb9cb,0xb899b984,0xbab3bb46,0x385f36aa,0xbb9cbb28,0xb4f3b726,0xb91fb9fa,0x3a253951,0xbc00bbe4,0xa452b147,0xb631b828,0x3b603ad6,
0xbbb0bbee,0x346f3036,0xae5fb3df,0x3bf63bc1,0xbafeba4f,0xb7c8b8ec,0xb9f4bab5,0x3958385d,0xbbd8bb82,0xb24bb587,0xb80ab90e,0x3ae83a33,
0xbbf3bbfe,0x2f27a97f,0xb2f7b5da,0x3bcf3b72,0xbb4cbbb7,0x368d3438,0x2dc9ac1f,0x3bf83bfc,0xbb5cbac2,0xb648b848,0xb911b9fe,0x3a31394d,
0xbbf9bbc4,0xad33b3ae,0xb5b1b802,0x3b7a3aed,0xbbc5bbf9,0x33a22d1a,0xa94db26f,0x3bfe3bd6,0xbac4bb5d,0x38453642,0x346f2fa4,0x3bb03bf1,
0xbba5bb25,0xb4b7b732,0xb80fb927,0x3ae53a1f,0xbbffbbee,0x2884b036,0xb24bb5b6,0x3bd83b79,0xbb76bbd6,0x35c8326f,0x305ba7da,0x3bed3bff,
0xba19bae0,0x392e3817,0x374234c9,0x3b213ba2,0xbbd9bb77,0xb232b5c2,0xb5ebb832,0x3b6f3ad0,0xbbe8bc00,0x30d7a57f,0xa81fb288,0x3bff3bd5,
0xbb07bb95,0x37a6351d,0x34f33080,0x3b9c3bec,0xb94fba43,0x39fc38fb,0x38ea3780,0x3a503b11,0xbbf8bbb6,0xadc9b444,0xb328b64e,0x3bcc3b5a,
0xbbb7bbf8,0x343e2db0,0x3042a9e3,0x3bee3bfe,0xba7abb36,0x38b236ee,0x379034ed,0x3b0d3b9d,0xb86ab989,0x3aac39c7,0x3a0438fb,0x39463a43,
0xbc00bbe2,0x2311b179,0xac9cb414,0x3bfb3bbc,0xbb6abbd7,0x36023257,0x34b72f40,0x3ba53bf3,0xb9d2babc,0x397d3852,0x38f83775,0x3a453b14,
0xb6ddb8b5,0x3b3a3a78,0x3ae83a0b,0x380a393e,0xbbf2bbfa,0x2f8bacb5,0x2d33af0e,0x3bf93bf4,0xbb04bb9e,0x37b234e1,0x372c3451,0x3b273bb4,
0xb911ba27,0x3a31391d,0x3a0038e2,0x394a3a56,0xb4c3b796,0x3ba33b0b,0x3b8b3ae6,0x3552380d,0x4c004c00,0x26480000,0x4c004c00,0x33113248,
0x4c004c00,0x2cb62a48,0x4c004c00,0x345233db,0x4c004c00,0x2fdb2e48,0x4c004c00,0x351b34b6,0x4c004c00,0x317f30b6,0x4bff4c00,0x35e4357f,
0x4c004c00,0x2fdb0000,0x4bfb4bfc,0x3c6a3bd9,0x4bff4c00,0x35e433db,0x4bf94bfa,0x3d653ce7,0x4bfe4bff,0x38e837da,0x4bf64bf7,0x3e5f3de2,
0x4bfd4bfe,0x3ade39e3,0x4bf24bf4,0x3f593edc,0x4c004c00,0x33110000,0x4bf04bf4,0x3fef3f0e,0x4bfe4bff,0x394d3711,0x4be84bed,0x40d74067,
0x4bfb4bfd,0x3c6a3b11,0x4bdf4be4,0x41b64147,0x4bf64bf9,0x3e2d3d4c,0x4bd44bda,0x42944226,0x4c004c00,0x351b0000,0x4bdf4be6,0x41b64115,
0x4bfc4bfe,0x3ba7391b,0x4bcf4bd7,0x42f74257,0x4bf64bf9,0x3e5f3d1a,0x4bbc4bc6,0x441a4396,0x4bec4bf1,0x40743fa4,0x4ba54bb1,0x44b74469,
0x4bff4c00,0x36ad0000,0x4bc84bd4,0x437142a1,0x4bfa4bfd,0x3d003aac,0x4bac4bbb,0x44874420,0x4bef4bf5,0x40293eaa,0x4b8b4b9d,0x455244ed,
0x4bde4be7,0x41cf40fd,0x4b654b79,0x461a45b6,0x4bff4c00,0x381f0000,0x4bab4bbc,0x44934414,0x4bf64bfc,0x3e2d3c1f,0x4b814b97,0x458d4511,
0x4be54bef,0x4122401d,0x4b4f4b69,0x46824608,0x4bcc4bda,0x43284226,0x4b164b33,0x476f46f9,0x4bfe4c00,0x38e80000,0x4b874ba0,0x456a44d5,
0x4bf24bfa,0x3f593ce7,0x4b4c4b6b,0x468d45fd,0x4bda4be8,0x421940e4,0x4b074b2b,0x47a6471b,0x4bb74bca,0x443e434c,0x4ab64ae0,0x485a4817,
0x4bfe4c00,0x39b10000,0x4b5e4b80,0x463c4593,0x4bee4bf8,0x40423db0,0x4b104b39,0x478546e3,0x4bce4be0,0x430f41aa,0x4ab34ae3,0x485f4812,
0x4b9e4bb7,0x44e74438,0x4a494a7f,0x48f348ab,0x4bfd4c00,0x3a7a0000,0x4b2f4b5a,0x470a464e,0x4be84bf6,0x40d73e78,0x4acb4aff,0x483a47c2,
0x4bbf4bd6,0x4402426f,0x4a544a92,0x48e54891,0x4b814ba2,0x458d44c9,0x49cd4a13,0x49824935,0x4bfd4c00,0x3b430000,0x4afb4b30,0x47d24705,
0x4be24bf3,0x416c3f40,0x4a7e4abf,0x48ad484d,0x4bae4bcb,0x447b4334,0x49eb4a37,0x49624909,0x4b604b8a,0x46314558,0x4946499b,0x4a0449b5,
0x4bfc4c00,0x3c060000,0x4ac14b02,0x484a47b7,0x4bdc4bf0,0x42014004,0x4a294a78,0x491b48b5,0x4b9c4bc0,0x44f343f7,0x497949d4,0x49d6497b,
0x4b3d4b70,0x46d245e5,0x48b24918,0x4a7a4a2b,0x4bfb4c00,0x3c6a0000,0x4a814ad0,0x48a84832,0x4bd44bed,0x42944067,0x49cd4a2b,0x49824918,
0x4b874bb2,0x456a445d,0x48fd4969,0x4a4149e5,0x4b164b53,0x476f4670,0x4815488c,0x4ae14a95,0x4bfa4c00,0x3cce0000,0x4a3d4a99,0x49024887,
0x4bcc4be9,0x432840cb,0x496b49d8,0x49e34976,0x4b714ba4,0x45df44bd,0x487a48f6,0x4aa24a47,0x4aeb4b33,0x480546f9,0x46dd47ee,0x4b3a4af3,
0x4bf94c00,0x3d330000,0x49f44a5e,0x495848d8,0x4bc34be5,0x43ba412e,0x49024980,0x4a3d49d0,0x4b594b95,0x4654451d,0x47dd487c,0x4af74aa0,
0x4abd4b11,0x48504780,0x458146b5,0x4b834b43,0x4bf84c00,0x3d970000,0x49a64a1f,0x49aa4927,0x4bba4be1,0x44264191,0x48944922,0x4a904a23,
0x4b3f4b84,0x46c6457c,0x46bb47f9,0x4b424af0,0x4a8c4aed,0x48994802,0x441a4570,0x4bbc4b86,0x4bf74c00,0x3dfb0000,0x495449dc,0x49f84972,
0x4bb04bdc,0x446f41f4,0x482048bf,0x4adb4a71,0x4b244b72,0x473745da,0x458d46ee,0x4b814b36,0x4a584ac6,0x48e04842,0x41534420,0x4be34bbb,
0x4bf64c00,0x3e5f0000,0x48fd4996,0x4a4149ba,0x4ba54bd7,0x44b74257,0x474e4858,0x4b1e4ab8,0x4b074b5f,0x47a64637,0x445745da,0x4bb34b72,
0x4a214a9c,0x49244881,0x3cce4191,0x4bfa4be1,0x4bf54c00,0x3ec30000,0x48a3494d,0x4a8549fe,0x4b9a4bd2,0x44ff42b9,0x465447d8,0x4b594af9,
0x4ae84b4b,0x480a4693,0x423244bd,0x4bd94ba4,0x49e74a71,0x496648bf,0xb4523db0,0x4c004bf8,0x4bf34c00,0x3f270000,0x48454900,0x4ac44a3f,
0x4b8e4bcd,0x4546431b,0x455246f9,0x4b8b4b33,0x4ac74b36,0x484046ee,0x3f594334,0x4bf24bcb,0x49aa4a43,0x49a648fb,0xbef52a48,0x4bf44c00,
0x4bf24c00,0x3f8b0000,0x47c848b0,0x4afe4a7c,0x4b814bc7,0x458d437d,0x444b4614,0x4bb54b67,0x4aa54b20,0x48744748,0x388440e4,0x4bff4be8,
0x496b4a13,0x49e34935,0xc263bd4c,0x4bd74bf9,0x4bf04c00,0x3fef0000,0x46ff485d,0x4b324ab5,0x4b734bc1,0x45d443df,0x427c4529,0x4bd64b93,
0x4a814b08,0x48a847a1,0xb9b13d1a,0x4bfe4bf9,0x492949e1,0x4a1d496d,0xc49fc160,0x4ba94be3,0x4bef4c00,0x40290000,0x46314807,0x4b604ae9,
0x4b654bbb,0x461a4420,0x405b4438,0x4bed4bb7,0x4a5c4af0,0x48db47f9,0xbfef2e48,0x4bf04c00,0x48e549ad,0x4a5449a4,0xc602c408,0x4b6a4bbe,
0x4bed4c00,0x405b0000,0x455e475e,0x4b894b1a,0x4b574bb4,0x465f4451,0x3c6a4288,0x4bfb4bd5,0x4a354ad6,0x490c4828,0xc27cbc51,0x4bd64bfb,
0x489e4976,0x4a8949d8,0xc759c558,0x4b1b4b8a,0x4beb4c00,0x408d0000,0x448746aa,0x4bac4b46,0x4b474bad,0x46a44481,0x26484099,0x4c004beb,
0x4a0d4abc,0x493c4852,0xc47bc080,0x4bae4bec,0x4855493e,0x4aba4a0b,0xc850c69e,0x4abd4b49,0x4be94c00,0x40be0000,0x435945f1,0x4bc94b6e,
0x4b374ba6,0x46e844b1,0xbc383d4c,0x4bfc4bf9,0x49e34aa0,0x496b487c,0xc5b1c2d2,0x4b7a4bd1,0x480a4905,0x4ae84a3b,0xc8eac7d8,0x4a504af9,
0x4be74c00,0x40f00000,0x419e4534,0x4be04b91,0x4b274b9e,0x472c44e1,0xc042357f,0x4bee4c00,0x49b84a83,0x499948a6,0xc6ddc48d,0x4b3a4bab,
0x477a48c9,0x4b134a69,0xc979c881,0x49d64a9c,0x4be54c00,0x41220000,0x3fbd4475,0x4bf14baf,0x4b164b97,0x476f4511,0xc263b91b,0x4bd74bfe,
0x498b4a65,0x49c548ce,0xc7fec5ab,0x4aee4b7b,0x46dd488c,0x4b3a4a95,0xc9fcc90e,0x494f4a33,0x4be34c00,0x41530000,0x3c384365,0x4bfc4bc9,
0x4b044b8f,0x47b24540,0xc43ebe78,0x4bb74bf6,0x495d4a47,0x49f048f6,0xc889c6c1,0x4a974b41,0x463c484d,0x4b5e4abf,0xca73c992,0x48bc49be,
0x4be14c00,0x41850000,0x317f41db,0x4c004bdd,0x4af14b86,0x47f34570,0xc546c12e,0x4b8e4be5,0x492e4a27,0x4a19491d,0xc90cc7cd,0x4a354afc,
0x4599480d,0x4b7f4ae6,0xcadbca0b,0x4820493e,0x4bdf4c00,0x41b60000,0xb9b1404e,0x4bfe4bed,0x4ade4b7d,0x481a459f,0xc648c31b,0x4b5c4bcd,
0x48fd4a07,0x4a414943,0xc986c867,0x49c94aae,0x44f34796,0x4b9c4b0b,0xcb35ca78,0x46f448b5,0x4bdd4c00,0x41e80000,0xbe5f3d7e,0x4bf64bf8,
0x4acb4b74,0x483a45ce,0xc742c481,0x4b214bad,0x48cc49e5,0x4a674969,0xc9f8c8e2,0x49544a56,0x444b4710,0x4bb54b2e,0xcb7fcad9,0x45994822,
0x4bda4c00,0x42190000,0xc0f038b6,0x4be74bff,0x4ab64b6b,0x485a45fd,0xc81ac570,0x4ade4b86,0x489949c3,0x4a8c498d,0xca60c956,0x48d649f6,
0x43404687,0x4bcb4b4e,0xcbb8cb2e,0x44324710,0x4bd84c00,0x424b0000,0xc2adb248,0x4bd34c00,0x4aa24b62,0x487a462b,0xc88ec659,0x4a934b58,
0x4865499f,0x4ab049b1,0xcabdc9c3,0x4850498d,0x41e845fd,0x4bdd4b6b,0xcbe1cb74,0x418545ce,0x4bd64c00,0x427c0000,0xc432bbd9,0x4bb84bfc,
0x4a8c4b58,0x48994659,0xc8fdc73d,0x4a414b22,0x4830497b,0x4ad149d4,0xcb10ca27,0x4785491d,0x408d4570,0x4beb4b86,0xcbf9cbad,0x3d334481,
0x4bd34c00,0x42ad0000,0xc50bbf0e,0x4b984bf4,0x4a764b4e,0x48b74687,0xc966c80d,0x49e74ae6,0x47f34956,0x4af149f6,0xcb57ca83,0x465f48a6,
0x3e5f44e1,0x4bf64b9e,0xcc00cbd7,0xb17f4257,0x4bd04c00,0x42de0000,0xc5dfc115,0x4b714be6,0x4a604b43,0x48d646b5,0xc9c9c877,0x49864aa3,
0x47854930,0x4b104a17,0xcb92cad6,0x452f4828,0x3b434451,0x4bfd4bb4,0xcbf5cbf3,0xbe913f40,0x4bce4c00,0x430f0000,0xc6afc2a1,0x4b454bd4,
0x4a494b39,0x48f346e3,0xca25c8dd,0x491f4a5a,0x47154909,0x4b2c4a37,0xcbc0cb20,0x43eb4748,0x3311437d,0x4c004bc7,0xcbd9cbff,0xc2323711,
0x4bcb4c00,0x43400000,0xc77ac414,0x4b134bbc,0x4a314b2e,0x49114710,0xca7ac93e,0x48b24a0b,0x46a448e2,0x4b474a56,0xcbe2cb5f,0x416c4637,
0xb7764257,0x4bff4bd7,0xcbaccbfd,0xc487bb75,0x4bc84c00,0x43710000,0xc820c4d5,0x4adb4ba0,0x4a194b22,0x492e473d,0xcac7c99b,0x484049b5,
0x463148ba,0x4b604a74,0xcbf8cb95,0x3dc9451d,0xbc9c412e,0x4bfb4be5,0xcb6fcbeb,0xc5ebc099,0x4bc54c00,0x43a20000,0xc87fc593,0x4a9e4b80,
0x4a004b17,0x494a476a,0xcb0dc9f2,0x4790495b,0x45bc4891,0x4b784a92,0xcc00cbc0,0x317f43f7,0xbf594004,0x4bf24bf0,0xcb21cbca,0xc742c34c,
0x4bc24c00,0x43d30000,0xc8dbc64e,0x4a5c4b5a,0x49e74b0b,0x49664796,0xcb4aca43,0x469948fb,0x45464867,0x4b8e4aae,0xcbfbcbe0,0xbc6a41aa,
0xc1093db0,0x4be64bf8,0xcac4cb9b,0xc845c4f9,0x4bbf4c00,0x44020000,0xc933c705,0x4a154b30,0x49cd4aff,0x498247c2,0xcb7fca8e,0x45994896,
0x44cf483d,0x4ba14ac9,0xcbe9cbf5,0xc0be3eaa,0xc2633aac,0x4bd74bfd,0xca58cb5d,0xc8e0c642,0x4bbc4c00,0x441a0000,0xc986c7b7,0x49c94b02,
0x49b34af3,0x499d47ee,0xcbabcad3,0x4493482d,0x44574812,0x4bb34ae3,0xcbcbcbff,0xc34037da,0xc3ba33db,0x4bc34c00,0xc9dfcb11,0xc970c780,
0x4bb84c00,0x44320000,0xc9d6c832,0x49794ad0,0x49994ae6,0x49b8480d,0xcbcecb11,0x430f4780,0x43ba47cd,0x4bc34afc,0xcb9fcbfe,0xc4dbb97f,
0xc487b57f,0x4bac4c00,0xc958cab8,0xc9f4c858,0x4bb54c00,0x444b0000,0xca21c887,0x49244a99,0x497d4ad9,0x49d24822,0xcbe7cb49,0x40f0469e,
0x42c64775,0x4bd24b14,0xcb68cbf2,0xc60ebf72,0xc52fbb75,0x4b924bfd,0xc8c7ca52,0xca6bc8e7,0x4bb24c00,0x44630000,0xca67c8d8,0x48cc4a5e,
0x49624acc,0x49eb4838,0xcbf8cb79,0x3d9745b6,0x41cf471b,0x4bde4b2b,0xcb24cbdb,0xc737c20d,0xc5d4be14,0x4b734bf7,0xc82ac9e1,0xcad5c96d,
0x4bae4c00,0x447b0000,0xcaa9c927,0x486f4a1f,0x49464abf,0x4a04484d,0xcc00cba2,0x351b44c9,0x40d746c1,0x4be84b41,0xcad5cbb9,0xc82ac42c,
0xc676c036,0x4b524bee,0xc70ac964,0xcb2fc9e9,0x4bab4c00,0x44930000,0xcae5c972,0x480f49dc,0x49294ab1,0x4a1d4862,0xcbfecbc4,0xba1643ae,
0x3fbd4665,0x4bf14b55,0xca7acb8c,0xc8b2c54c,0xc715c160,0x4b2c4be3,0xc5b1c8dd,0xcb7aca5a,0x4ba74c00,0x44ab0000,0xcb1bc9ba,0x47594996,
0x490c4aa3,0x4a354877,0xcbf2cbdf,0xbf5941c3,0x3dc94608,0x4bf84b69,0xca15cb55,0xc933c665,0xc7b2c288,0x4b044bd5,0xc44bc84d,0xcbb5cabf,
0x4ba34c00,0x44c30000,0xcb4cc9fe,0x468d494d,0x48ee4a95,0x4a4d488c,0xcbdecbf1,0xc1cf3fa4,0x3ba745ab,0x4bfc4b7b,0xc9a6cb14,0xc9aac775,
0xc825c3ae,0x4ad84bc4,0xc1b6c76a,0xcbdfcb17,0x4b9f4c00,0x44db0000,0xcb78ca3f,0x45bc4900,0x48d14a87,0x4a6448a0,0xcbc0cbfd,0xc3eb3b75,
0x3776454c,0x4bff4b8c,0xc92ecac9,0xca19c83d,0xc86fc469,0x4aa94bb1,0xbd97c62b,0xcbf8cb62,0x4b9c4c00,0x44f30000,0xcb9eca7c,0x44e748b0,
0x48b24a78,0x4a7a48b5,0xcb9acc00,0xc4ffaa48,0xa64844ed,0x4c004b9d,0xc8adca74,0xca7ec8ba,0xc8b7c4f9,0x4a764b9b,0x2cb6c4e1,0xcc00cb9e,
0x4b984c00,0x450b0000,0xcbbdcab5,0x440e485d,0x48944a69,0x4a9048c9,0xcb6acbfc,0xc602bc1f,0xb81f448d,0x4bff4bab,0xc825ca17,0xcad8c930,
0xc8fdc587,0x4a414b82,0x3e2dc31b,0xcbf6cbcd,0x4b944c00,0x45230000,0xcbd7cae9,0x42634807,0x48744a5a,0x4aa548dd,0xcb32cbf0,0xc6ffc004,
0xbc06442c,0x4bfc4bb9,0xc72cc9b1,0xcb27c99f,0xc941c614,0x4a094b67,0x4201c067,0xcbdccbed,0x4b904c00,0x453a0000,0xcbeacb1a,0x40a6475e,
0x48554a4b,0x4aba48f1,0xcaf1cbdc,0xc7f3c1f4,0xbdfb4396,0x4bf74bc6,0xc602c943,0xcb6aca07,0xc982c69e,0x49cd4b49,0x446fbaac,0xcbb0cbfd,
0x4b8b4c00,0x45520000,0xcbf8cb46,0x3dc946aa,0x48354a3b,0x4ace4905,0xcaa9cbc1,0xc86fc3df,0xbfef42d2,0x4bf04bd1,0xc4cfc8ce,0xcba1ca65,
0xc9c0c726,0x49904b28,0x45d43852,0xcb73cbff,0x4b874c00,0x456a0000,0xcbffcb6e,0x388445f1,0x48154a2b,0x4ae14918,0xca58cb9e,0xc8e0c4e1,
0xc0f0420d,0x4be74bdb,0xc328c852,0xcbcccabc,0xc9fcc7ac,0x494f4b05,0x472c3fa4,0xcb27cbf1,0x4b834c00,0x45810000,0xcc00cb91,0xb51b4534,
0x47e84a1b,0x4af4492b,0xca00cb74,0xc94ac5ce,0xc1e84147,0x4bdd4be4,0xc0a6c7a1,0xcbeacb08,0xca35c817,0x490c4ae0,0x483a4288,0xcacbcbd5,
0x4b7f4c00,0x45990000,0xcbfacbaf,0xbcce4475,0x47a64a0b,0x4b07493e,0xc9a1cb43,0xc9afc6b5,0xc2de4080,0x4bd04bec,0xbc38c693,0xcbfccb4b,
0xca6bc858,0x48c74ab8,0x48d64499,0xca60cbaa,0x4b7a4c00,0x45b10000,0xcbefcbc9,0xc0294365,0x476449fa,0x4b184951,0xc93ccb0b,0xca0dc796,
0xc3d33f72,0x4bc24bf2,0x3311c57c,0xcc00cb84,0xca9ec896,0x487f4a8e,0x496645e5,0xc9e7cb70,0x4b764c00,0x45c80000,0xcbddcbdd,0xc1e841db,
0x472149e9,0x4b2a4964,0xc8d1cacc,0xca64c838,0xc4633de2,0x4bb24bf7,0x3dfbc45d,0xcbf7cbb2,0xcacec8d3,0x48354a62,0x49eb4726,0xc962cb28,
0x4b714c00,0x45df0000,0xcbc5cbed,0xc3a2404e,0x46dd49d8,0x4b3a4976,0xc85fca87,0xcab3c8a0,0xc4db3c51,0x4b9f4bfb,0x4185c26f,0xcbe1cbd6,
0xcafbc90e,0x47d24a33,0x4a64482d,0xc8d1cad3,0x4b6c4c00,0x45f70000,0xcba7cbf8,0xc4ab3d7e,0x469949c7,0x4b4a4989,0xc7d2ca3b,0xcafbc905,
0xc552397f,0x4b8b4bfe,0x4402c01d,0xcbbfcbef,0xcb24c948,0x47374a02,0x4ace48bf,0xc835ca71,0x4b684c00,0x460e0000,0xcb83cbff,0xc58138b6,
0x465449b5,0x4b59499b,0xc6ddc9e9,0xcb3ac964,0xc5c834b6,0x4b764c00,0x453abb11,0xcb90cbfd,0xcb4ac980,0x469949d0,0x4b2a4948,0xc721ca02,
0x2c002c00,0x2c002c00,0x2c002c00,0x2c002c00,0x2b642c00,0x261f29a8,0xa61f0000,0xab64a9a8,0x29a82c00,0xa9a80000,0xa9a8ac00,0x29a80000,
0x261f2c00,0xab64a9a8,0x2b640000,0xa61f29a8,0x2c00,0xac00,0x2c00,0xac00,0xa61f2c00,0x2b64a9a8,0xab640000,0x261f29a8,
0xa9a82c00,0x29a80000,0x29a8ac00,0xa9a80000,0xab642c00,0xa61f29a8,0x261f0000,0x2b64a9a8,0,0,0,0,
0x261f0000,0x2b6429a8,0x2b642c00,0x261f29a8,0x29a80000,0x29a82c00,0xa9a80000,0xa9a8ac00,0x2b640000,0xa61f29a8,0xa61fac00,0x2b6429a8,
0x2c000000,0xac000000,0x2c000000,0xac000000,0x2b640000,0xa61fa9a8,0xa61f2c00,0x2b64a9a8,0x29a80000,0x29a8ac00,0xa9a80000,0xa9a82c00,
0x261f0000,0x2b64a9a8,0x2b64ac00,0x261fa9a8,0xac002c00,0xac002c00,0xac002c00,0xac002c00,0xab642c00,0xa61f29a8,0x261f0000,0x2b64a9a8,
0xa9a82c00,0x29a80000,0x29a8ac00,0xa9a80000,0xa61f2c00,0x2b64a9a8,0xab640000,0x261f29a8,0x2c00,0xac00,0x2c00,0xac00,
0x261f2c00,0xab64a9a8,0x2b640000,0xa61f29a8,0x29a82c00,0xa9a80000,0xa9a8ac00,0x29a80000,0x2b642c00,0x261f29a8,0xa61f0000,0xab64a9a8,
0,0,0,0,0xa61f0000,0xab6429a8,0xab642c00,0xa61f29a8,0xa9a80000,0xa9a82c00,0x29a80000,0x29a8ac00,
0xab640000,0x261f29a8,0x261fac00,0xab6429a8,0xac000000,0x2c000000,0xac000000,0x2c000000,0xab640000,0x261fa9a8,0x261f2c00,0xab64a9a8,
0xa9a80000,0xa9a8ac00,0x29a80000,0x29a82c00,0xa61f0000,0xab64a9a8,0xab64ac00,0xa61fa9a8,0,0,0,0,
0xa61f0000,0xab64a9a8,0xab64ac00,0xa61fa9a8,0xa9a80000,0xa9a8ac00,0x29a80000,0x29a82c00,0xab640000,0x261fa9a8,0x261f2c00,0xab64a9a8,
0xac000000,0x2c000000,0xac000000,0x2c000000,0xab640000,0x261f29a8,0x261fac00,0xab6429a8,0xa9a80000,0xa9a82c00,0x29a80000,0x29a8ac00,
0xa61f0000,0xab6429a8,0xab642c00,0xa61f29a8,0x2c002c00,0x2c002c00,0x2c002c00,0x2c002c00,0x2b642c00,0x261f29a8,0xa61f0000,0xab64a9a8,
0x29a82c00,0xa9a80000,0xa9a8ac00,0x29a80000,0x261f2c00,0xab64a9a8,0x2b640000,0xa61f29a8,0x2c00,0xac00,0x2c00,0xac00,
0xa61f2c00,0x2b64a9a8,0xab640000,0x261f29a8,0xa9a82c00,0x29a80000,0x29a8ac00,0xa9a80000,0xab642c00,0xa61f29a8,0x261f0000,0x2b64a9a8,
0,0,0,0,0x261f0000,0x2b64a9a8,0x2b64ac00,0x261fa9a8,0x29a80000,0x29a8ac00,0xa9a80000,0xa9a82c00,
0x2b640000,0xa61fa9a8,0xa61f2c00,0x2b64a9a8,0x2c000000,0xac000000,0x2c000000,0xac000000,0x2b640000,0xa61f29a8,0xa61fac00,0x2b6429a8,
0x29a80000,0x29a82c00,0xa9a80000,0xa9a8ac00,0x261f0000,0x2b6429a8,0x2b642c00,0x261f29a8,0xac002c00,0xac002c00,0xac002c00,0xac002c00,
0xab642c00,0xa61f29a8,0x261f0000,0x2b64a9a8,0xa9a82c00,0x29a80000,0x29a8ac00,0xa9a80000,0xa61f2c00,0x2b64a9a8,0xab640000,0x261f29a8,
0x2c00,0xac00,0x2c00,0xac00,0x261f2c00,0xab64a9a8,0x2b640000,0xa61f29a8,0x29a82c00,0xa9a80000,0xa9a8ac00,0x29a80000,
0x2b642c00,0x261f29a8,0xa61f0000,0xab64a9a8,0x2c002c00,0x2c002c00,0x2c002c00,0x2c002c00,0xab64ac00,0xa61fa9a8,0x261f0000,0x2b6429a8,
0x29a82c00,0xa9a80000,0xa9a8ac00,0x29a80000,0xa61fac00,0x2b6429a8,0xab640000,0x261fa9a8,0x2c00,0xac00,0x2c00,0xac00,
0x261fac00,0xab6429a8,0x2b640000,0xa61fa9a8,0xa9a82c00,0x29a80000,0x29a8ac00,0xa9a80000,0x2b64ac00,0x261fa9a8,0xa61f0000,0xab6429a8,
0,0,0,0,0xa61f0000,0xab64a9a8,0xab64ac00,0xa61fa9a8,0x29a80000,0x29a82c00,0xa9a80000,0xa9a8ac00,
0xab640000,0x261fa9a8,0x261f2c00,0xab64a9a8,0x2c000000,0xac000000,0x2c000000,0xac000000,0xab640000,0x261f29a8,0x261fac00,0xab6429a8,
0x29a80000,0x29a8ac00,0xa9a80000,0xa9a82c00,0xa61f0000,0xab6429a8,0xab642c00,0xa61f29a8,0xac002c00,0xac002c00,0xac002c00,0xac002c00,
0x2b64ac00,0x261fa9a8,0xa61f0000,0xab6429a8,0xa9a82c00,0x29a80000,0x29a8ac00,0xa9a80000,0x261fac00,0xab6429a8,0x2b640000,0xa61fa9a8,
0x2c00,0xac00,0x2c00,0xac00,0xa61fac00,0x2b6429a8,0xab640000,0x261fa9a8,0x29a82c00,0xa9a80000,0xa9a8ac00,0x29a80000,
0xab64ac00,0xa61fa9a8,0x261f0000,0x2b6429a8,0,0,0,0,0x261f0000,0x2b64a9a8,0x2b64ac00,0x261fa9a8,
0xa9a80000,0xa9a82c00,0x29a80000,0x29a8ac00,0x2b640000,0xa61fa9a8,0xa61f2c00,0x2b64a9a8,0xac000000,0x2c000000,0xac000000,0x2c000000,
0x2b640000,0xa61f29a8,0xa61fac00,0x2b6429a8,0xa9a80000,0xa9a8ac00,0x29a80000,0x29a82c00,0x261f0000,0x2b6429a8,0x2b642c00,0x261f29a8,
0,0,0,0,0x261f0000,0x2b6429a8,0x2b642c00,0x261f29a8,0xa9a80000,0xa9a8ac00,0x29a80000,0x29a82c00,
0x2b640000,0xa61f29a8,0xa61fac00,0x2b6429a8,0xac000000,0x2c000000,0xac000000,0x2c000000,0x2b640000,0xa61fa9a8,0xa61f2c00,0x2b64a9a8,
0xa9a80000,0xa9a82c00,0x29a80000,0x29a8ac00,0x261f0000,0x2b64a9a8,0x2b64ac00,0x261fa9a8,0x2c002c00,0x2c002c00,0x2c002c00,0x2c002c00,
0xab64ac00,0xa61fa9a8,0x261f0000,0x2b6429a8,0x29a82c00,0xa9a80000,0xa9a8ac00,0x29a80000,0xa61fac00,0x2b6429a8,0xab640000,0x261fa9a8,
0x2c00,0xac00,0x2c00,0xac00,0x261fac00,0xab6429a8,0x2b640000,0xa61fa9a8,0xa9a82c00,0x29a80000,0x29a8ac00,0xa9a80000,
0x2b64ac00,0x261fa9a8,0xa61f0000,0xab6429a8,0,0,0,0,0xa61f0000,0xab6429a8,0xab642c00,0xa61f29a8,
0x29a80000,0x29a8ac00,0xa9a80000,0xa9a82c00,0xab640000,0x261f29a8,0x261fac00,0xab6429a8,0x2c000000,0xac000000,0x2c000000,0xac000000,
0xab640000,0x261fa9a8,0x261f2c00,0xab64a9a8,0x29a80000,0x29a82c00,0xa9a80000,0xa9a8ac00,0xa61f0000,0xab64a9a8,0xab64ac00,0xa61fa9a8,
0xac002c00,0xac002c00,0xac002c00,0xac002c00,0x2b64ac00,0x261fa9a8,0xa61f0000,0xab6429a8,0xa9a82c00,0x29a80000,0x29a8ac00,0xa9a80000,
0x261fac00,0xab6429a8,0x2b640000,0xa61fa9a8,0x2c00,0xac00,0x2c00,0xac00,0xa61fac00,0x2b6429a8,0xab640000,0x261fa9a8,
0x29a82c00,0xa9a80000,0xa9a8ac00,0x29a80000,0xab64ac00,0xa61fa9a8,0x261f0000,0x2b6429a8,0x2bd92c00,0x2aa72b64,0x287229a8,0x223e261f,
0x2aa72c00,0xa23e261f,0xabd9a9a8,0xa872ab64,0x28722c00,0xabd9a61f,0x223ea9a8,0x2aa72b64,0x223e2c00,0xa872ab64,0x2aa729a8,0xabd9a61f,
0xa23e2c00,0x2872ab64,0xaaa729a8,0x2bd9a61f,0xa8722c00,0x2bd9a61f,0xa23ea9a8,0xaaa72b64,0xaaa72c00,0x223e261f,0x2bd9a9a8,0x2872ab64,
0xabd92c00,0xaaa72b64,0xa87229a8,0xa23e261f,0x223e0000,0x2872261f,0x2aa729a8,0x2bd92b64,0x28720000,0x2bd92b64,0x223e29a8,0xaaa7a61f,
0x2aa70000,0x223e2b64,0xabd9a9a8,0x2872a61f,0x2bd90000,0xaaa7261f,0x2872a9a8,0xa23e2b64,0x2bd90000,0xaaa7a61f,0x287229a8,0xa23eab64,
0x2aa70000,0x223eab64,0xabd929a8,0x2872261f,0x28720000,0x2bd9ab64,0x223ea9a8,0xaaa7261f,0x223e0000,0x2872a61f,0x2aa7a9a8,0x2bd9ab64,
0xabd92c00,0xaaa72b64,0xa87229a8,0xa23e261f,0xaaa72c00,0x223e261f,0x2bd9a9a8,0x2872ab64,0xa8722c00,0x2bd9a61f,0xa23ea9a8,0xaaa72b64,
0xa23e2c00,0x2872ab64,0xaaa729a8,0x2bd9a61f,0x223e2c00,0xa872ab64,0x2aa729a8,0xabd9a61f,0x28722c00,0xabd9a61f,0x223ea9a8,0x2aa72b64,
0x2aa72c00,0xa23e261f,0xabd9a9a8,0xa872ab64,0x2bd92c00,0x2aa72b64,0x287229a8,0x223e261f,0xa23e0000,0xa872261f,0xaaa729a8,0xabd92b64,
0xa8720000,0xabd92b64,0xa23e29a8,0x2aa7a61f,0xaaa70000,0xa23e2b64,0x2bd9a9a8,0xa872a61f,0xabd90000,0x2aa7261f,0xa872a9a8,0x223e2b64,
0xabd90000,0x2aa7a61f,0xa87229a8,0x223eab64,0xaaa70000,0xa23eab64,0x2bd929a8,0xa872261f,0xa8720000,0xabd9ab64,0xa23ea9a8,0x2aa7261f,
0xa23e0000,0xa872a61f,0xaaa7a9a8,0xabd9ab64,0xa23e0000,0xa872a61f,0xaaa7a9a8,0xabd9ab64,0xa8720000,0xabd9ab64,0xa23ea9a8,0x2aa7261f,
0xaaa70000,0xa23eab64,0x2bd929a8,0xa872261f,0xabd90000,0x2aa7a61f,0xa87229a8,0x223eab64,0xabd90000,0x2aa7261f,0xa872a9a8,0x223e2b64,
0xaaa70000,0xa23e2b64,0x2bd9a9a8,0xa872a61f,0xa8720000,0xabd92b64,0xa23e29a8,0x2aa7a61f,0xa23e0000,0xa872261f,0xaaa729a8,0xabd92b64,
0x2bd92c00,0x2aa72b64,0x287229a8,0x223e261f,0x2aa72c00,0xa23e261f,0xabd9a9a8,0xa872ab64,0x28722c00,0xabd9a61f,0x223ea9a8,0x2aa72b64,
0x223e2c00,0xa872ab64,0x2aa729a8,0xabd9a61f,0xa23e2c00,0x2872ab64,0xaaa729a8,0x2bd9a61f,0xa8722c00,0x2bd9a61f,0xa23ea9a8,0xaaa72b64,
0xaaa72c00,0x223e261f,0x2bd9a9a8,0x2872ab64,0xabd92c00,0xaaa72b64,0xa87229a8,0xa23e261f,0x223e0000,0x2872a61f,0x2aa7a9a8,0x2bd9ab64,
0x28720000,0x2bd9ab64,0x223ea9a8,0xaaa7261f,0x2aa70000,0x223eab64,0xabd929a8,0x2872261f,0x2bd90000,0xaaa7a61f,0x287229a8,0xa23eab64,
0x2bd90000,0xaaa7261f,0x2872a9a8,0xa23e2b64,0x2aa70000,0x223e2b64,0xabd9a9a8,0x2872a61f,0x28720000,0x2bd92b64,0x223e29a8,0xaaa7a61f,
0x223e0000,0x2872261f,0x2aa729a8,0x2bd92b64,0xabd92c00,0xaaa72b64,0xa87229a8,0xa23e261f,0xaaa72c00,0x223e261f,0x2bd9a9a8,0x2872ab64,
0xa8722c00,0x2bd9a61f,0xa23ea9a8,0xaaa72b64,0xa23e2c00,0x2872ab64,0xaaa729a8,0x2bd9a61f,0x223e2c00,0xa872ab64,0x2aa729a8,0xabd9a61f,
0x28722c00,0xabd9a61f,0x223ea9a8,0x2aa72b64,0x2aa72c00,0xa23e261f,0xabd9a9a8,0xa872ab64,0x2bd92c00,0x2aa72b64,0x287229a8,0x223e261f,
0xa23e0000,0xa872a61f,0xaaa7a9a8,0xabd9ab64,0x28720000,0x2bd92b64,0x223e29a8,0xaaa7a61f,0xaaa70000,0xa23eab64,0x2bd929a8,0xa872261f,
0x2bd90000,0xaaa7261f,0x2872a9a8,0xa23e2b64,0xabd90000,0x2aa7261f,0xa872a9a8,0x223e2b64,0x2aa70000,0x223eab64,0xabd929a8,0x2872261f,
0xa8720000,0xabd92b64,0xa23e29a8,0x2aa7a61f,0x223e0000,0x2872a61f,0x2aa7a9a8,0x2bd9ab64,0x2bd92c00,0x2aa72b64,0x287229a8,0x223e261f,
0xaaa7ac00,0x223ea61f,0x2bd929a8,0x28722b64,0x28722c00,0xabd9a61f,0x223ea9a8,0x2aa72b64,0xa23eac00,0x28722b64,0xaaa7a9a8,0x2bd9261f,
0xa23e2c00,0x2872ab64,0xaaa729a8,0x2bd9a61f,0x2872ac00,0xabd9261f,0x223e29a8,0x2aa7ab64,0xaaa72c00,0x223e261f,0x2bd9a9a8,0x2872ab64,
0x2bd9ac00,0x2aa7ab64,0x2872a9a8,0x223ea61f,0x223e0000,0x2872a61f,0x2aa7a9a8,0x2bd9ab64,0xa8720000,0xabd92b64,0xa23e29a8,0x2aa7a61f,
0x2aa70000,0x223eab64,0xabd929a8,0x2872261f,0xabd90000,0x2aa7261f,0xa872a9a8,0x223e2b64,0x2bd90000,0xaaa7261f,0x2872a9a8,0xa23e2b64,
0xaaa70000,0xa23eab64,0x2bd929a8,0xa872261f,0x28720000,0x2bd92b64,0x223e29a8,0xaaa7a61f,0xa23e0000,0xa872a61f,0xaaa7a9a8,0xabd9ab64,
0xabd92c00,0xaaa72b64,0xa87229a8,0xa23e261f,0x2aa7ac00,0xa23ea61f,0xabd929a8,0xa8722b64,0xa8722c00,0x2bd9a61f,0xa23ea9a8,0xaaa72b64,
0x223eac00,0xa8722b64,0x2aa7a9a8,0xabd9261f,0x223e2c00,0xa872ab64,0x2aa729a8,0xabd9a61f,0xa872ac00,0x2bd9261f,0xa23e29a8,0xaaa7ab64,
0x2aa72c00,0xa23e261f,0xabd9a9a8,0xa872ab64,0xabd9ac00,0xaaa7ab64,0xa872a9a8,0xa23ea61f,0xabd9ac00,0xaaa7ab64,0xa872a9a8,0xa23ea61f,
0x2aa72c00,0xa23e261f,0xabd9a9a8,0xa872ab64,0xa872ac00,0x2bd9261f,0xa23e29a8,0xaaa7ab64,0x223e2c00,0xa872ab64,0x2aa729a8,0xabd9a61f,
0x223eac00,0xa8722b64,0x2aa7a9a8,0xabd9261f,0xa8722c00,0x2bd9a61f,0xa23ea9a8,0xaaa72b64,0x2aa7ac00,0xa23ea61f,0xabd929a8,0xa8722b64,
0xabd92c00,0xaaa72b64,0xa87229a8,0xa23e261f,0xa23e0000,0xa872a61f,0xaaa7a9a8,0xabd9ab64,0x28720000,0x2bd92b64,0x223e29a8,0xaaa7a61f,
0xaaa70000,0xa23eab64,0x2bd929a8,0xa872261f,0x2bd90000,0xaaa7261f,0x2872a9a8,0xa23e2b64,0xabd90000,0x2aa7261f,0xa872a9a8,0x223e2b64,
0x2aa70000,0x223eab64,0xabd929a8,0x2872261f,0xa8720000,0xabd92b64,0xa23e29a8,0x2aa7a61f,0x223e0000,0x2872a61f,0x2aa7a9a8,0x2bd9ab64,
0x2bd9ac00,0x2aa7ab64,0x2872a9a8,0x223ea61f,0xaaa72c00,0x223e261f,0x2bd9a9a8,0x2872ab64,0x2872ac00,0xabd9261f,0x223e29a8,0x2aa7ab64,
0xa23e2c00,0x2872ab64,0xaaa729a8,0x2bd9a61f,0xa23eac00,0x28722b64,0xaaa7a9a8,0x2bd9261f,0x28722c00,0xabd9a61f,0x223ea9a8,0x2aa72b64,
0xaaa7ac00,0x223ea61f,0x2bd929a8,0x28722b64,0x2bd92c00,0x2aa72b64,0x287229a8,0x223e261f,0x223e0000,0x2872a61f,0x2aa7a9a8,0x2bd9ab64,
0xa8720000,0xabd92b64,0xa23e29a8,0x2aa7a61f,0x2aa70000,0x223eab64,0xabd929a8,0x2872261f,0xabd90000,0x2aa7261f,0xa872a9a8,0x223e2b64,
0x2bd90000,0xaaa7261f,0x2872a9a8,0xa23e2b64,0xaaa70000,0xa23eab64,0x2bd929a8,0xa872261f,0x28720000,0x2bd92b64,0x223e29a8,0xaaa7a61f,
0xa23e0000,0xa872a61f,0xaaa7a9a8,0xabd9ab64,0x27fe2800,0x96480000,0x273b2764,0xa2d7a21f,0x27ea27f6,0x9cb29a46,0x26dd270e,0xa41da38b,
0x27c327d9,0x9fc69e3e,0x266d26a7,0xa4c4a472,0x278827a8,0xa164a0a5,0x25ed262f,0xa55fa513,0x27c32800,0x9fc60000,0xa4c4a21f,0xa66da764,
0x25ed270e,0xa55fa38b,0xa73ba62f,0xa2d7a513,0x21642472,0xa788a6a7,0xa7fea7d9,0x16489e3e,0x9cb21a46,0xa7eaa7f6,0xa6dda7a8,0x241d20a5,
0x273b2800,0xa2d70000,0xa55fa764,0x25ed221f,0x1fc62513,0xa7c3a62f,0x1cb2a0a5,0x27ea27a8,0xa4c49e3e,0xa66da7d9,0x26dd2472,0x241d26a7,
0xa7fea70e,0x9648a38b,0x278827f6,0xa1641a46,0x266d2800,0xa4c40000,0x26dd221f,0x241d2764,0xa16420a5,0xa788a7a8,0x25ed27f6,0xa55f9a46,
0xa7fea6a7,0x1648a472,0xa2d71e3e,0xa73ba7d9,0x9fc6a62f,0x27c32513,0xa7eaa70e,0x1cb2a38b,0x255f2800,0xa5ed0000,0x21642764,0xa788a21f,
0xa66d9a46,0xa4c4a7f6,0xa7c3a38b,0x9fc6a70e,0xa41da7d9,0x26dd1e3e,0x9cb2a6a7,0x27ea2472,0x273b20a5,0x22d727a8,0x27fe2513,0x1648262f,
0x241d2800,0xa6dd0000,0xa7eaa21f,0x9cb2a764,0xa7fea38b,0x9648a70e,0x2164a513,0x2788262f,0x22d7a472,0x273b26a7,0x255f27d9,0xa5ed1e3e,
0x24c427f6,0xa66d1a46,0xa7c3a0a5,0x9fc6a7a8,0x21642800,0xa7880000,0x1648a764,0x27fe221f,0xa6dda62f,0x241da513,0x24c427a8,0xa66d20a5,
0x27ea1e3e,0x1cb227d9,0xa7c3a472,0x1fc6a6a7,0xa55f238b,0xa5eda70e,0x273b9a46,0x22d727f6,0x1cb22800,0xa7ea0000,0x27c3221f,0x9fc62764,
0xa2d7a7a8,0x273ba0a5,0xa7fe9a46,0x9648a7f6,0x255f26a7,0xa5ed2472,0x27889e3e,0x216427d9,0xa6dda513,0x241da62f,0xa66d238b,0xa4c4a70e,
0x96482800,0xa7fe0000,0xa2d72764,0xa73ba21f,0x1cb2a7f6,0x27ea1a46,0x241da70e,0x26dd238b,0x9fc627d9,0xa7c39e3e,0xa4c426a7,0xa66da472,
0x2164a7a8,0x278820a5,0x255fa62f,0x25ed2513,0x9fc62800,0xa7c30000,0xa66da21f,0x24c4a764,0x255fa70e,0x25ed238b,0x22d7262f,0xa73b2513,
0xa7882472,0xa164a6a7,0x1648a7d9,0x27fe9e3e,0x27ea9a46,0x9cb227f6,0xa41d27a8,0xa6dda0a5,0xa2d72800,0xa73b0000,0x25eda764,0x255f221f,
0x27c3a513,0x1fc6262f,0xa7ea20a5,0x1cb2a7a8,0xa66d9e3e,0x24c4a7d9,0x241d2472,0xa6dd26a7,0x1648270e,0xa7fe238b,0x2164a7f6,0x27889a46,
0xa4c42800,0xa66d0000,0x241d221f,0xa6dd2764,0x2788a0a5,0xa16427a8,0x255fa7f6,0x25ed1a46,0x1648a6a7,0x27fea472,0xa73b1e3e,0x22d7a7d9,
0xa7c3262f,0x9fc6a513,0x9cb2270e,0xa7ea238b,0xa5ed2800,0xa55f0000,0xa7882764,0xa164a21f,0x24c41a46,0xa66d27f6,0x1fc6238b,0xa7c3270e,
0x26dda7d9,0x241d1e3e,0x27eaa6a7,0x1cb22472,0xa2d7a0a5,0x273ba7a8,0x9648a513,0x27fea62f,0xa6dd2800,0xa41d0000,0x9cb2a21f,0x27eaa764,
0x1648238b,0xa7fe270e,0xa7882513,0x2164a62f,0x273ba472,0xa2d726a7,0xa5ed27d9,0xa55f1e3e,0x266da7f6,0x24c49a46,0x1fc620a5,0xa7c327a8,
0xa7882800,0xa1640000,0x27fea764,0x9648221f,0xa41d262f,0xa6dd2513,0x266da7a8,0x24c4a0a5,0x1cb21e3e,0xa7ea27d9,0x1fc6a472,0x27c3a6a7,
0x25eda38b,0xa55f270e,0xa2d71a46,0x273ba7f6,0xa7ea2800,0x9cb20000,0x9fc6221f,0xa7c32764,0xa73b27a8,0xa2d720a5,0x16481a46,0xa7fe27f6,
0xa5ed26a7,0xa55f2472,0x21649e3e,0xa78827d9,0xa41d2513,0xa6dd262f,0x24c4a38b,0xa66d270e,0xa7fe2800,0x16480000,0xa73b2764,0x22d7a21f,
0xa7ea27f6,0x1cb29a46,0xa6dd270e,0x241da38b,0xa7c327d9,0x1fc69e3e,0xa66d26a7,0x24c4a472,0xa78827a8,0x2164a0a5,0xa5ed262f,0x255fa513,
0xa7c32800,0x1fc60000,0x24c4a21f,0x266da764,0xa5ed270e,0x255fa38b,0x273ba62f,0x22d7a513,0xa1642472,0x2788a6a7,0x27fea7d9,0x96489e3e,
0x1cb21a46,0x27eaa7f6,0x26dda7a8,0xa41d20a5,0xa73b2800,0x22d70000,0x255fa764,0xa5ed221f,0x9fc62513,0x27c3a62f,0x9cb2a0a5,0xa7ea27a8,
0x24c49e3e,0x266da7d9,0xa6dd2472,0xa41d26a7,0x27fea70e,0x1648a38b,0xa78827f6,0x21641a46,0xa66d2800,0x24c40000,0xa6dd221f,0xa41d2764,
0x216420a5,0x2788a7a8,0xa5ed27f6,0x255f9a46,0x27fea6a7,0x9648a472,0x22d71e3e,0x273ba7d9,0x1fc6a62f,0xa7c32513,0x27eaa70e,0x9cb2a38b,
0xa55f2800,0x25ed0000,0xa1642764,0x2788a21f,0x266d9a46,0x24c4a7f6,0x27c3a38b,0x1fc6a70e,0x241da7d9,0xa6dd1e3e,0x1cb2a6a7,0xa7ea2472,
0xa73b20a5,0xa2d727a8,0xa7fe2513,0x9648262f,0xa41d2800,0x26dd0000,0x27eaa21f,0x1cb2a764,0x27fea38b,0x1648a70e,0xa164a513,0xa788262f,
0xa2d7a472,0xa73b26a7,0xa55f27d9,0x25ed1e3e,0xa4c427f6,0x266d1a46,0x27c3a0a5,0x1fc6a7a8,0xa1642800,0x27880000,0x9648a764,0xa7fe221f,
0x26dda62f,0xa41da513,0xa4c427a8,0x266d20a5,0xa7ea1e3e,0x9cb227d9,0x27c3a472,0x9fc6a6a7,0x255f238b,0x25eda70e,0xa73b9a46,0xa2d727f6,
0x9cb22800,0x27ea0000,0xa7c3221f,0x1fc62764,0x22d7a7a8,0xa73ba0a5,0x27fe9a46,0x1648a7f6,0xa55f26a7,0x25ed2472,0xa7889e3e,0xa16427d9,
0x26dda513,0xa41da62f,0x266d238b,0x24c4a70e,0x16482800,0x27fe0000,0x22d72764,0x273ba21f,0x9cb2a7f6,0xa7ea1a46,0xa41da70e,0xa6dd238b,
0x1fc627d9,0x27c39e3e,0x24c426a7,0x266da472,0xa164a7a8,0xa78820a5,0xa55fa62f,0xa5ed2513,0x1fc62800,0x27c30000,0x266da21f,0xa4c4a764,
0xa55fa70e,0xa5ed238b,0xa2d7262f,0x273b2513,0x27882472,0x2164a6a7,0x9648a7d9,0xa7fe9e3e,0xa7ea9a46,0x1cb227f6,0x241d27a8,0x26dda0a5,
0x22d72800,0x273b0000,0xa5eda764,0xa55f221f,0xa7c3a513,0x9fc6262f,0x27ea20a5,0x9cb2a7a8,0x266d9e3e,0xa4c4a7d9,0xa41d2472,0x26dd26a7,
0x9648270e,0x27fe238b,0xa164a7f6,0xa7889a46,0x24c42800,0x266d0000,0xa41d221f,0x26dd2764,0xa788a0a5,0x216427a8,0xa55fa7f6,0xa5ed1a46,
0x9648a6a7,0xa7fea472,0x273b1e3e,0xa2d7a7d9,0x27c3262f,0x1fc6a513,0x1cb2270e,0x27ea238b,0x25ed2800,0x255f0000,0x27882764,0x2164a21f,
0xa4c41a46,0x266d27f6,0x9fc6238b,0x27c3270e,0xa6dda7d9,0xa41d1e3e,0xa7eaa6a7,0x9cb22472,0x22d7a0a5,0xa73ba7a8,0x1648a513,0xa7fea62f,
0x26dd2800,0x241d0000,0x1cb2a21f,0xa7eaa764,0x9648238b,0x27fe270e,0x27882513,0xa164a62f,0xa73ba472,0x22d726a7,0x25ed27d9,0x255f1e3e,
0xa66da7f6,0xa4c49a46,0x9fc620a5,0x27c327a8,0x27882800,0x21640000,0xa7fea764,0x1648221f,0x241d262f,0x26dd2513,0xa66da7a8,0xa4c4a0a5,
0x9cb21e3e,0x27ea27d9,0x9fc6a472,0xa7c3a6a7,0xa5eda38b,0x255f270e,0x22d71a46,0xa73ba7f6,0x27ea2800,0x1cb20000,0x1fc6221f,0x27c32764,
0x273b27a8,0x22d720a5,0x96481a46,0x27fe27f6,0x25ed26a7,0x255f2472,0xa1649e3e,0x278827d9,0x241d2513,0x26dd262f,0xa4c4a38b,0x266d270e,
0x255f25a8,0xa5eda5a8,0x2164221f,0xa788a764,0x24c42513,0xa66da62f,0x1fc620a5,0xa7c3a7a8,0x241d2472,0xa6dda6a7,0x1cb21e3e,0xa7eaa7d9,
0x22d7238b,0xa73ba70e,0x16481a46,0xa7fea7f6,0xa41da5a8,0x26dd25a8,0x27ea2764,0x1cb2221f,0x9648a0a5,0x27fe27a8,0x278827f6,0xa1649a46,
0x22d71e3e,0x273b27d9,0x255f26a7,0xa5eda472,0x266d2513,0x24c4262f,0x1fc6238b,0xa7c3a70e,0x216425a8,0xa788a5a8,0x1648a21f,0x27fe2764,
0xa41d9a46,0xa6dda7f6,0x266d238b,0x24c4270e,0xa7eaa6a7,0x9cb2a472,0x27c327d9,0x9fc61e3e,0xa5eda7a8,0x255f20a5,0x22d7262f,0xa73ba513,
0x9cb2a5a8,0x27ea25a8,0xa7c3a764,0x1fc6a21f,0x273b238b,0x22d7270e,0x9648a513,0x27fe262f,0x255f27d9,0xa5ed9e3e,0x27882472,0x216426a7,
0xa41d1a46,0xa6dda7f6,0x24c427a8,0xa66da0a5,0x964825a8,0xa7fea5a8,0xa2d7221f,0xa73ba764,0xa7eaa62f,0x1cb2a513,0xa6dda7a8,0x241da0a5,
0x1fc6a472,0x27c326a7,0x24c49e3e,0x266d27d9,0x2788270e,0xa164238b,0x25ed27f6,0xa55f1a46,0x1fc6a5a8,0x27c325a8,0x266d2764,0xa4c4221f,
0x25ed27a8,0xa55f20a5,0xa73b9a46,0xa2d7a7f6,0xa7889e3e,0xa164a7d9,0x1648a6a7,0x27fe2472,0x1cb2a62f,0x27ea2513,0x26dd270e,0xa41d238b,
0xa2d725a8,0xa73ba5a8,0x25eda21f,0x255f2764,0x9fc6a7f6,0x27c31a46,0x9cb2270e,0xa7eaa38b,0x266d26a7,0xa4c42472,0xa41da7d9,0x26dd9e3e,
0xa7fea0a5,0x9648a7a8,0x27882513,0xa164262f,0x24c4a5a8,0x266d25a8,0xa41da764,0x26dda21f,0xa164270e,0xa788a38b,0x25ed262f,0xa55f2513,
0x1648a7d9,0x27fe1e3e,0xa73ba472,0x22d7a6a7,0x1fc627f6,0xa7c31a46,0x27ea20a5,0x9cb227a8,0xa5ed25a8,0xa55fa5a8,0xa788221f,0xa164a764,
0x266da513,0x24c4262f,0x27c3a0a5,0x1fc627a8,0xa6dd2472,0xa41da6a7,0xa7ea1e3e,0x9cb2a7d9,0x273ba38b,0x22d7270e,0x27fe9a46,0x164827f6,
0x26dda5a8,0x241d25a8,0x1cb22764,0xa7ea221f,0xa7fe20a5,0x9648a7a8,0x2164a7f6,0x27881a46,0x273b1e3e,0xa2d727d9,0xa5ed26a7,0xa55fa472,
0xa4c4a513,0x266da62f,0x27c3a38b,0x1fc6270e,0xa78825a8,0xa164a5a8,0x27fea21f,0x96482764,0x26dd1a46,0xa41d27f6,0xa4c4a38b,0x266da70e,
0x9cb2a6a7,0x27eaa472,0x9fc627d9,0xa7c31e3e,0xa55f27a8,0xa5eda0a5,0x273ba62f,0x22d72513,0x27eaa5a8,0x1cb225a8,0x1fc6a764,0x27c3a21f,
0xa2d7a38b,0x273ba70e,0xa7fe2513,0x9648a62f,0xa5ed27d9,0xa55f9e3e,0x21642472,0xa78826a7,0x26dd9a46,0xa41d27f6,0x266da7a8,0x24c420a5,
0xa7fe25a8,0x1648a5a8,0xa73b221f,0x22d7a764,0x9cb2262f,0xa7ea2513,0xa41d27a8,0xa6dd20a5,0x27c3a472,0x9fc626a7,0x266d9e3e,0xa4c427d9,
0x2164a70e,0x2788a38b,0x255fa7f6,0x25ed9a46,0x27c3a5a8,0x9fc625a8,0xa4c42764,0xa66d221f,0x255fa7a8,0x25eda0a5,0x22d71a46,0xa73b27f6,
0xa1649e3e,0x2788a7d9,0x27fea6a7,0x96482472,0xa7ea262f,0x1cb2a513,0x241da70e,0x26dda38b,0xa73b25a8,0x22d7a5a8,0x255fa21f,0xa5ed2764,
0xa7c327f6,0x9fc69a46,0x27eaa70e,0x9cb2238b,0xa4c426a7,0xa66d2472,0x26dda7d9,0x241d9e3e,0x164820a5,0xa7fe27a8,0x2164a513,0x2788a62f,
0x266da5a8,0xa4c425a8,0x26dda764,0x241da21f,0x2788a70e,0xa164238b,0x255fa62f,0x25eda513,0x27fea7d9,0x96481e3e,0x22d7a472,0x273ba6a7,
0x27c3a7f6,0x1fc69a46,0x1cb2a0a5,0x27eaa7a8,0xa55f25a8,0x25eda5a8,0xa164221f,0x2788a764,0xa4c42513,0x266da62f,0x9fc620a5,0x27c3a7a8,
0xa41d2472,0x26dda6a7,0x9cb21e3e,0x27eaa7d9,0xa2d7238b,0x273ba70e,0x96481a46,0x27fea7f6,0x241da5a8,0xa6dd25a8,0xa7ea2764,0x9cb2221f,
0x1648a0a5,0xa7fe27a8,0xa78827f6,0x21649a46,0xa2d71e3e,0xa73b27d9,0xa55f26a7,0x25eda472,0xa66d2513,0xa4c4262f,0x9fc6238b,0x27c3a70e,
0xa16425a8,0x2788a5a8,0x9648a21f,0xa7fe2764,0x241d9a46,0x26dda7f6,0xa66d238b,0xa4c4270e,0x27eaa6a7,0x1cb2a472,0xa7c327d9,0x1fc61e3e,
0x25eda7a8,0xa55f20a5,0xa2d7262f,0x273ba513,0x1cb2a5a8,0xa7ea25a8,0x27c3a764,0x9fc6a21f,0xa73b238b,0xa2d7270e,0x1648a513,0xa7fe262f,
0xa55f27d9,0x25ed9e3e,0xa7882472,0xa16426a7,0x241d1a46,0x26dda7f6,0xa4c427a8,0x266da0a5,0x164825a8,0x27fea5a8,0x22d7221f,0x273ba764,
0x27eaa62f,0x9cb2a513,0x26dda7a8,0xa41da0a5,0x9fc6a472,0xa7c326a7,0xa4c49e3e,0xa66d27d9,0xa788270e,0x2164238b,0xa5ed27f6,0x255f1a46,
0x9fc6a5a8,0xa7c325a8,0xa66d2764,0x24c4221f,0xa5ed27a8,0x255f20a5,0x273b9a46,0x22d7a7f6,0x27889e3e,0x2164a7d9,0x9648a6a7,0xa7fe2472,
0x9cb2a62f,0xa7ea2513,0xa6dd270e,0x241d238b,0x22d725a8,0x273ba5a8,0xa5eda21f,0xa55f2764,0x1fc6a7f6,0xa7c31a46,0x1cb2270e,0x27eaa38b,
0xa66d26a7,0x24c42472,0x241da7d9,0xa6dd9e3e,0x27fea0a5,0x1648a7a8,0xa7882513,0x2164262f,0xa4c4a5a8,0xa66d25a8,0x241da764,0xa6dda21f,
0x2164270e,0x2788a38b,0xa5ed262f,0x255f2513,0x9648a7d9,0xa7fe1e3e,0x273ba472,0xa2d7a6a7,0x9fc627f6,0x27c31a46,0xa7ea20a5,0x1cb227a8,
0x25ed25a8,0x255fa5a8,0x2788221f,0x2164a764,0xa66da513,0xa4c4262f,0xa7c3a0a5,0x9fc627a8,0x26dd2472,0x241da6a7,0x27ea1e3e,0x1cb2a7d9,
0xa73ba38b,0xa2d7270e,0xa7fe9a46,0x964827f6,0xa6dda5a8,0xa41d25a8,0x9cb22764,0x27ea221f,0x27fe20a5,0x1648a7a8,0xa164a7f6,0xa7881a46,
0xa73b1e3e,0x22d727d9,0x25ed26a7,0x255fa472,0x24c4a513,0xa66da62f,0xa7c3a38b,0x9fc6270e,0x278825a8,0x2164a5a8,0xa7fea21f,0x16482764,
0xa6dd1a46,0x241d27f6,0x24c4a38b,0xa66da70e,0x1cb2a6a7,0xa7eaa472,0x1fc627d9,0x27c31e3e,0x255f27a8,0x25eda0a5,0xa73ba62f,0xa2d72513,
0xa7eaa5a8,0x9cb225a8,0x9fc6a764,0xa7c3a21f,0x22d7a38b,0xa73ba70e,0x27fe2513,0x1648a62f,0x25ed27d9,0x255f9e3e,0xa1642472,0x278826a7,
0xa6dd9a46,0x241d27f6,0xa66da7a8,0xa4c420a5,0x27fe25a8,0x9648a5a8,0x273b221f,0xa2d7a764,0x1cb2262f,0x27ea2513,0x241d27a8,0x26dd20a5,
0xa7c3a472,0x1fc626a7,0xa66d9e3e,0x24c427d9,0xa164a70e,0xa788a38b,0xa55fa7f6,0xa5ed9a46,0xa7c3a5a8,0x1fc625a8,0x24c42764,0x266d221f,
0xa55fa7a8,0xa5eda0a5,0xa2d71a46,0x273b27f6,0x21649e3e,0xa788a7d9,0xa7fea6a7,0x16482472,0x27ea262f,0x9cb2a513,0xa41da70e,0xa6dda38b,
0x273b25a8,0xa2d7a5a8,0xa55fa21f,0x25ed2764,0x27c327f6,0x1fc69a46,0xa7eaa70e,0x1cb2238b,0x24c426a7,0x266d2472,0xa6dda7d9,0xa41d9e3e,
0x964820a5,0x27fe27a8,0xa164a513,0xa788a62f,0xa66da5a8,0x24c425a8,0xa6dda764,0xa41da21f,0xa788a70e,0x2164238b,0xa55fa62f,0xa5eda513,
0xa7fea7d9,0x16481e3e,0xa2d7a472,0xa73ba6a7,0xa7c3a7f6,0x9fc69a46,0x9cb2a0a5,0xa7eaa7a8,
};

#define PROF(slot) do {} while (0)
#define PROF3(slot) do {} while (0)
#define PROF2(slot) do {} while (0)

__device__ __forceinline__ uint32_t smem_u32(const void* p) { return (uint32_t)__cvta_generic_to_shared(p); }

__device__ __forceinline__ void mbar_init(uint32_t a, uint32_t c) {
  asm volatile("mbarrier.init.shared::cta.b64 [%0], %1;\n" ::"r"(a), "r"(c) : "memory");
}
__device__ __forceinline__ void mbar_expect_tx(uint32_t a, uint32_t bytes) {
  asm volatile("mbarrier.arrive.expect_tx.shared::cta.b64 _, [%0], %1;\n" ::"r"(a), "r"(bytes) : "memory");
}
__device__ __forceinline__ void mbar_arrive_cluster(uint32_t cluster_addr) {
  asm volatile("mbarrier.arrive.shared::cluster.b64 _, [%0];\n" ::"r"(cluster_addr) : "memory");
}
__device__ __forceinline__ void mbar_arrive_cluster_n(uint32_t cluster_addr, uint32_t n) {
  asm volatile("mbarrier.arrive.shared::cluster.b64 _, [%0], %1;\n" ::"r"(cluster_addr), "r"(n) : "memory");
}
__device__ __forceinline__ bool mbar_try(uint32_t a, uint32_t parity) {
  uint32_t ok;
  asm volatile("{\n.reg .pred p;\nmbarrier.try_wait.parity.shared::cta.b64 p, [%1], %2;\nselp.u32 %0, 1, 0, p;\n}\n"
               : "=r"(ok) : "r"(a), "r"(parity) : "memory");
  return ok;
}
__device__ __forceinline__ void mbar_wait(uint32_t a, uint32_t parity) {
  if (mbar_try(a, parity)) return;
#pragma unroll 1
  for (int n = 0; n < SPIN_LIMIT; n++)
    if (mbar_try(a, parity)) break;
}
__device__ __forceinline__ void mbar_wait_idle(uint32_t a, uint32_t parity) {
#pragma unroll 1
  for (int n = 0; n < SPIN_LIMIT; n++) {
    uint32_t ok;
    asm volatile("{\n.reg .pred p;\nmbarrier.try_wait.parity.shared::cta.b64 p, [%1], %2, %3;\nselp.u32 %0, 1, 0, p;\n}\n"
                 : "=r"(ok) : "r"(a), "r"(parity), "r"(4000) : "memory");
    if (ok) break;
  }
}
__device__ __forceinline__ bool elect_one() {
  uint32_t p;
  asm volatile("{\n.reg .pred P;\nelect.sync _|P, 0xffffffff;\nselp.u32 %0, 1, 0, P;\n}\n" : "=r"(p));
  return p;
}
__device__ __forceinline__ uint32_t mapa(uint32_t a, uint32_t rank) {
  uint32_t r;
  asm volatile("mapa.shared::cluster.u32 %0, %1, %2;\n" : "=r"(r) : "r"(a), "r"(rank));
  return r;
}
__device__ __forceinline__ void nb_sync(int id, int n) { asm volatile("bar.sync %0, %1;\n" ::"r"(id), "r"(n) : "memory"); }
__device__ __forceinline__ void nb_arrive(int id, int n) { asm volatile("bar.arrive %0, %1;\n" ::"r"(id), "r"(n) : "memory"); }
__device__ __forceinline__ void cluster_sync_all() {
  asm volatile("barrier.cluster.arrive.relaxed.aligned;\nbarrier.cluster.wait.aligned;\n" ::: "memory");
}
__device__ __forceinline__ void fence_async_smem() { asm volatile("fence.proxy.async.shared::cta;\n" ::: "memory"); }
__device__ __forceinline__ void fence_async_all() { asm volatile("fence.proxy.async.global;\n" ::: "memory"); }

__device__ __forceinline__ void tma_load_3d(uint32_t dst, const CUtensorMap* tm, uint32_t bar, int c0, int c1, int c2) {
  asm volatile(
      "cp.async.bulk.tensor.3d.shared::cluster.global.mbarrier::complete_tx::bytes [%0], [%1, {%3, %4, %5}], [%2];\n"
      ::"r"(dst), "l"(tm), "r"(bar), "r"(c0), "r"(c1), "r"(c2) : "memory");
}
__device__ __forceinline__ void tma_load_4d(uint32_t dst, const CUtensorMap* tm, uint32_t bar, int c0, int c1, int c2, int c3) {
  asm volatile(
      "cp.async.bulk.tensor.4d.shared::cluster.global.mbarrier::complete_tx::bytes [%0], [%1, {%3, %4, %5, %6}], [%2];\n"
      ::"r"(dst), "l"(tm), "r"(bar), "r"(c0), "r"(c1), "r"(c2), "r"(c3) : "memory");
}
__device__ __forceinline__ void tma_load_3d_mc(uint32_t dst, const CUtensorMap* tm, uint32_t bar, int c0, int c1, int c2) {
  asm volatile(
      "cp.async.bulk.tensor.3d.shared::cluster.global.mbarrier::complete_tx::bytes.multicast::cluster [%0], [%1, {%3, %4, %5}], [%2], %6;\n"
      ::"r"(dst), "l"(tm), "r"(bar), "r"(c0), "r"(c1), "r"(c2), "h"((uint16_t)3) : "memory");
}
__device__ __forceinline__ void tma_load_5d(uint32_t dst, const CUtensorMap* tm, uint32_t bar, int c0, int c4) {
  asm volatile(
      "cp.async.bulk.tensor.5d.shared::cluster.global.mbarrier::complete_tx::bytes [%0], [%1, {%3, %5, %5, %5, %4}], [%2];\n"
      ::"r"(dst), "l"(tm), "r"(bar), "r"(c0), "r"(c4), "r"(0) : "memory");
}
__device__ __forceinline__ void bulk_load(uint32_t dst, const void* src, uint32_t bytes, uint32_t bar) {
  asm volatile("cp.async.bulk.shared::cluster.global.mbarrier::complete_tx::bytes [%0], [%1], %2, [%3];\n"
               ::"r"(dst), "l"(src), "r"(bytes), "r"(bar) : "memory");
}
__device__ __forceinline__ void bulk_commit() { asm volatile("cp.async.bulk.commit_group;\n" ::: "memory"); }
__device__ __forceinline__ void bulk_wait0() { asm volatile("cp.async.bulk.wait_group 0;\n" ::: "memory"); }
__device__ __forceinline__ void prefetch_tmap(const CUtensorMap* tm) {
  asm volatile("prefetch.tensormap [%0];\n" ::"l"(tm) : "memory");
}

__device__ __forceinline__ void wg_fence() { asm volatile("wgmma.fence.sync.aligned;\n" ::: "memory"); }
__device__ __forceinline__ void wg_commit() { asm volatile("wgmma.commit_group.sync.aligned;\n" ::: "memory"); }
template <int N> __device__ __forceinline__ void wg_wait() {
  asm volatile("wgmma.wait_group.sync.aligned %0;\n" ::"n"(N) : "memory");
}
__device__ __forceinline__ uint64_t mkdesc(uint32_t addr, uint32_t lbo, uint32_t sbo, uint32_t swz) {
  return (uint64_t)((addr & 0x3FFFF) >> 4) | ((uint64_t)(lbo >> 4) << 16) | ((uint64_t)(sbo >> 4) << 32) |
         ((uint64_t)swz << 62);
}

#define R4(d, o) "+f"(d[o + 0]), "+f"(d[o + 1]), "+f"(d[o + 2]), "+f"(d[o + 3])
#define R8(d, o) R4(d, o), R4(d, o + 4)
#define R16(d, o) R8(d, o), R8(d, o + 8)
#define R32(d, o) R16(d, o), R16(d, o + 16)
#define R64(d, o) R32(d, o), R32(d, o + 32)

__device__ __forceinline__ void wgmma_n192(float (&d)[96], uint64_t da, uint64_t db, uint32_t acc) {
  asm volatile(
      "{\n.reg .pred p;\nsetp.ne.u32 p, %98, 0;\n"
      "wgmma.mma_async.sync.aligned.m64n192k16.f32.bf16.bf16 "
      "{%0,%1,%2,%3,%4,%5,%6,%7,%8,%9,%10,%11,%12,%13,%14,%15,%16,%17,%18,%19,%20,%21,%22,%23,%24,%25,%26,%27,%28,%29,%30,%31,"
      "%32,%33,%34,%35,%36,%37,%38,%39,%40,%41,%42,%43,%44,%45,%46,%47,%48,%49,%50,%51,%52,%53,%54,%55,%56,%57,%58,%59,%60,%61,%62,%63,"
      "%64,%65,%66,%67,%68,%69,%70,%71,%72,%73,%74,%75,%76,%77,%78,%79,%80,%81,%82,%83,%84,%85,%86,%87,%88,%89,%90,%91,%92,%93,%94,%95}, "
      "%96, %97, p, 1, 1, 0, 1;\n}\n"
      : R64(d, 0), R32(d, 64)
      : "l"(da), "l"(db), "r"(acc));
}
__device__ __forceinline__ void wgmma_n128(float (&d)[64], uint64_t da, uint64_t db, uint32_t acc) {
  asm volatile(
      "{\n.reg .pred p;\nsetp.ne.u32 p, %66, 0;\n"
      "wgmma.mma_async.sync.aligned.m64n128k16.f32.bf16.bf16 "
      "{%0,%1,%2,%3,%4,%5,%6,%7,%8,%9,%10,%11,%12,%13,%14,%15,%16,%17,%18,%19,%20,%21,%22,%23,%24,%25,%26,%27,%28,%29,%30,%31,"
      "%32,%33,%34,%35,%36,%37,%38,%39,%40,%41,%42,%43,%44,%45,%46,%47,%48,%49,%50,%51,%52,%53,%54,%55,%56,%57,%58,%59,%60,%61,%62,%63}, "
      "%64, %65, p, 1, 1, 0, 1;\n}\n"
      : R64(d, 0)
      : "l"(da), "l"(db), "r"(acc));
}
template <int N> __device__ __forceinline__ void fence_regs(float (&d)[N]) {
#pragma unroll
  for (int i = 0; i < N; i++) asm volatile("" : "+f"(d[i])::"memory");
}

__device__ __forceinline__ void mma16816(float (&d)[4], uint32_t a0, uint32_t a1, uint32_t a2, uint32_t a3, uint32_t b0,
                                         uint32_t b1) {
  asm("mma.sync.aligned.m16n8k16.row.col.f32.bf16.bf16.f32 {%0,%1,%2,%3}, {%4,%5,%6,%7}, {%8,%9}, {%0,%1,%2,%3};\n"
      : "+f"(d[0]), "+f"(d[1]), "+f"(d[2]), "+f"(d[3])
      : "r"(a0), "r"(a1), "r"(a2), "r"(a3), "r"(b0), "r"(b1));
}
__device__ __forceinline__ void mma16816_z(float (&d)[4], uint32_t a0, uint32_t a1, uint32_t a2, uint32_t a3, uint32_t b0,
                                           uint32_t b1) {
  asm("mma.sync.aligned.m16n8k16.row.col.f32.bf16.bf16.f32 {%0,%1,%2,%3}, {%4,%5,%6,%7}, {%8,%9}, {%10,%10,%10,%10};\n"
      : "=f"(d[0]), "=f"(d[1]), "=f"(d[2]), "=f"(d[3])
      : "r"(a0), "r"(a1), "r"(a2), "r"(a3), "r"(b0), "r"(b1), "f"(0.f));
}
__device__ __forceinline__ void ldsm4t(uint32_t (&r)[4], uint32_t a) {
  asm volatile("ldmatrix.sync.aligned.m8n8.x4.trans.shared.b16 {%0,%1,%2,%3}, [%4];\n"
               : "=r"(r[0]), "=r"(r[1]), "=r"(r[2]), "=r"(r[3]) : "r"(a) : "memory");
}
__device__ __forceinline__ void ldsm2t(uint32_t& r0, uint32_t& r1, uint32_t a) {
  asm volatile("ldmatrix.sync.aligned.m8n8.x2.trans.shared.b16 {%0,%1}, [%2];\n" : "=r"(r0), "=r"(r1) : "r"(a) : "memory");
}
__device__ __forceinline__ void st_async128(uint32_t a, uint32_t bar, uint32_t x, uint32_t y, uint32_t z, uint32_t w) {
  asm volatile("st.async.weak.shared::cluster.mbarrier::complete_tx::bytes.v4.b32 [%0], {%2,%3,%4,%5}, [%1];\n"
               ::"r"(a), "r"(bar), "r"(x), "r"(y), "r"(z), "r"(w) : "memory");
}
__device__ __forceinline__ void mbar_arrive(uint32_t a) {
  asm volatile("mbarrier.arrive.shared::cta.b64 _, [%0];\n" ::"r"(a) : "memory");
}
__device__ __forceinline__ void stsm4(uint32_t a, uint32_t r0, uint32_t r1, uint32_t r2, uint32_t r3) {
  asm volatile("stmatrix.sync.aligned.m8n8.x4.shared.b16 [%0], {%1,%2,%3,%4};\n"
               ::"r"(a), "r"(r0), "r"(r1), "r"(r2), "r"(r3) : "memory");
}
__device__ __forceinline__ void stsm4t(uint32_t a, uint32_t r0, uint32_t r1, uint32_t r2, uint32_t r3) {
  asm volatile("stmatrix.sync.aligned.m8n8.x4.trans.shared.b16 [%0], {%1,%2,%3,%4};\n"
               ::"r"(a), "r"(r0), "r"(r1), "r"(r2), "r"(r3) : "memory");
}
__device__ __forceinline__ uint2 lds64(uint32_t a) {
  uint2 v;
  asm volatile("ld.shared.v2.u32 {%0,%1}, [%2];\n" : "=r"(v.x), "=r"(v.y) : "r"(a));
  return v;
}
__device__ __forceinline__ uint4 lds128(uint32_t a) {
  uint4 v;
  asm volatile("ld.shared.v4.u32 {%0,%1,%2,%3}, [%4];\n" : "=r"(v.x), "=r"(v.y), "=r"(v.z), "=r"(v.w) : "r"(a) : "memory");
  return v;
}
__device__ __forceinline__ void sts128(uint32_t a, uint32_t x, uint32_t y, uint32_t z, uint32_t w) {
  asm volatile("st.shared.v4.u32 [%0], {%1,%2,%3,%4};\n" ::"r"(a), "r"(x), "r"(y), "r"(z), "r"(w) : "memory");
}
__device__ __forceinline__ uint32_t pack_bf16(float lo, float hi) {
  uint32_t r;
  asm("cvt.rn.bf16x2.f32 %0, %1, %2;\n" : "=r"(r) : "f"(hi), "f"(lo));
  return r;
}
__device__ __forceinline__ uint32_t bmul2(uint32_t a, uint32_t b) {
  uint32_t r;
  asm("mul.rn.bf16x2 %0, %1, %2;\n" : "=r"(r) : "r"(a), "r"(b));
  return r;
}
__device__ __forceinline__ uint32_t bmax2(uint32_t a, uint32_t b) {
  uint32_t r;
  asm("max.bf16x2 %0, %1, %2;\n" : "=r"(r) : "r"(a), "r"(b));
  return r;
}
__device__ __forceinline__ uint32_t bfma2(uint32_t a, uint32_t b, uint32_t c) {
  uint32_t r;
  asm("fma.rn.bf16x2 %0, %1, %2, %3;\n" : "=r"(r) : "r"(a), "r"(b), "r"(c));
  return r;
}
__device__ __forceinline__ uint32_t badd2(uint32_t a, uint32_t b) {
  uint32_t r;
  asm("add.rn.bf16x2 %0, %1, %2;\n" : "=r"(r) : "r"(a), "r"(b));
  return r;
}
__device__ __forceinline__ void prefetch_l2(const void* p) { asm volatile("prefetch.global.L2 [%0];\n" ::"l"(p)); }
__device__ __forceinline__ void cp_async16n(uint32_t dst, const void* src) {
  asm volatile("cp.async.cg.shared.global [%0], [%1], 16;\n" ::"r"(dst), "l"(src) : "memory");
}
__device__ __forceinline__ void cp_async16(uint32_t dst, const void* src, uint32_t srcbytes) {
  asm volatile("cp.async.cg.shared.global.L2::256B [%0], [%1], 16, %2;\n" ::"r"(dst), "l"(src), "r"(srcbytes) : "memory");
}
__device__ __forceinline__ uint32_t ld_acquire(const uint32_t* p) {
  uint32_t v;
  asm volatile("ld.acquire.gpu.global.u32 %0, [%1];\n" : "=r"(v) : "l"(p) : "memory");
  return v;
}
__device__ __forceinline__ uint32_t ld_relaxed(const uint32_t* p) {
  uint32_t v;
  asm volatile("ld.relaxed.gpu.global.u32 %0, [%1];\n" : "=r"(v) : "l"(p) : "memory");
  return v;
}
__device__ __forceinline__ void st_release(uint32_t* p, uint32_t v) {
  asm volatile("st.release.gpu.global.u32 [%0], %1;\n" ::"l"(p), "r"(v) : "memory");
}
__device__ __forceinline__ void wait_flag(const uint32_t* p, uint32_t want) {
  int n = 0;
  while (ld_relaxed(p) != want && ++n < SPIN_LIMIT) __nanosleep(40);
  (void)ld_acquire(p);
}

struct Params {
  const __nv_bfloat16* x;
  const __nv_bfloat16* w;
  const __nv_bfloat16* q;
  const __nv_bfloat16* k;
  const __nv_bfloat16* v;
  const __nv_bfloat16* shift_k;
  const __nv_bfloat16* ssm_k;
  const __nv_bfloat16* ssm_D;
  const __nv_bfloat16* wo;
  __nv_bfloat16* out;
};

__device__ __forceinline__ uint32_t lds32(uint32_t a) {
  uint32_t v;
  asm volatile("ld.shared.u32 %0, [%1];\n" : "=r"(v) : "r"(a));
  return v;
}
#define W4(d, o) "=f"(d[o + 0]), "=f"(d[o + 1]), "=f"(d[o + 2]), "=f"(d[o + 3])
#define W8(d, o) W4(d, o), W4(d, o + 4)
#define W16(d, o) W8(d, o), W8(d, o + 8)
#define U4(c, d, o) c(d[o + 0]), c(d[o + 1]), c(d[o + 2]), c(d[o + 3])
#define U8(c, d, o) U4(c, d, o), U4(c, d, o + 4)
#define U16(c, d, o) U8(c, d, o), U8(c, d, o + 8)
#define U32(c, d, o) U16(c, d, o), U16(c, d, o + 16)
#define D32 "{%0,%1,%2,%3,%4,%5,%6,%7,%8,%9,%10,%11,%12,%13,%14,%15,%16,%17,%18,%19,%20,%21,%22,%23,%24,%25,%26,%27,%28,%29,%30,%31}"
#define D16 "{%0,%1,%2,%3,%4,%5,%6,%7,%8,%9,%10,%11,%12,%13,%14,%15}"
#define D8 "{%0,%1,%2,%3,%4,%5,%6,%7}"
template <int ACC> __device__ __forceinline__ void hmma_n128t(uint32_t (&d)[32], const uint32_t (&a)[4], uint64_t db) {
  if (ACC)
    asm volatile("wgmma.mma_async.sync.aligned.m64n128k16.f16.f16.f16 " D32 ", {%32,%33,%34,%35}, %36, 1, 1, 1, 1;\n"
                 : U32("+r", d, 0) : "r"(a[0]), "r"(a[1]), "r"(a[2]), "r"(a[3]), "l"(db));
  else
    asm volatile("wgmma.mma_async.sync.aligned.m64n128k16.f16.f16.f16 " D32 ", {%32,%33,%34,%35}, %36, 0, 1, 1, 1;\n"
                 : U32("=r", d, 0) : "r"(a[0]), "r"(a[1]), "r"(a[2]), "r"(a[3]), "l"(db));
}
template <int ACC, int TB> __device__ __forceinline__ void hmma_n32(uint32_t (&d)[8], const uint32_t (&a)[4], uint64_t db) {
  if (ACC)
    asm volatile("wgmma.mma_async.sync.aligned.m64n32k16.f16.f16.f16 " D8 ", {%8,%9,%10,%11}, %12, 1, 1, 1, %13;\n"
                 : U8("+r", d, 0) : "r"(a[0]), "r"(a[1]), "r"(a[2]), "r"(a[3]), "l"(db), "n"(TB));
  else
    asm volatile("wgmma.mma_async.sync.aligned.m64n32k16.f16.f16.f16 " D8 ", {%8,%9,%10,%11}, %12, 0, 1, 1, %13;\n"
                 : U8("=r", d, 0) : "r"(a[0]), "r"(a[1]), "r"(a[2]), "r"(a[3]), "l"(db), "n"(TB));
}
template <int N> __device__ __forceinline__ void fence_regs(uint32_t (&d)[N]) {
#pragma unroll
  for (int i = 0; i < N; i++) asm volatile("" : "+r"(d[i])::"memory");
}
__device__ __forceinline__ uint32_t hmul(uint32_t a, uint32_t b) { uint32_t r; asm("mul.rn.f16x2 %0, %1, %2;\n" : "=r"(r) : "r"(a), "r"(b)); return r; }
__device__ __forceinline__ uint32_t hadd(uint32_t a, uint32_t b) { uint32_t r; asm("add.rn.f16x2 %0, %1, %2;\n" : "=r"(r) : "r"(a), "r"(b)); return r; }
__device__ __forceinline__ uint32_t hsub(uint32_t a, uint32_t b) { uint32_t r; asm("sub.rn.f16x2 %0, %1, %2;\n" : "=r"(r) : "r"(a), "r"(b)); return r; }
__device__ __forceinline__ uint32_t hfma(uint32_t a, uint32_t b, uint32_t c) { uint32_t r; asm("fma.rn.f16x2 %0, %1, %2, %3;\n" : "=r"(r) : "r"(a), "r"(b), "r"(c)); return r; }
__device__ __forceinline__ uint32_t hfnma(uint32_t a, uint32_t b, uint32_t c) {
  uint32_t r;
  asm("{\n.reg .b32 t;\nneg.f16x2 t, %1;\nfma.rn.f16x2 %0, t, %2, %3;\n}\n" : "=r"(r) : "r"(a), "r"(b), "r"(c));
  return r;
}
__device__ __forceinline__ uint32_t hrefl(uint32_t p, uint32_t s) {
  uint32_t r;
  asm("{\n.reg .b32 t;\nneg.f16x2 t, %2;\nfma.rn.f16x2 %0, %1, %3, t;\n}\n" : "=r"(r) : "r"(p), "r"(s), "r"(0x40004000u));
  return r;
}
__device__ __forceinline__ void bfly(uint32_t xr, uint32_t xi, uint32_t tr, uint32_t ti, uint32_t yr, uint32_t yi, uint32_t ur,
                                     uint32_t ui, uint32_t& sr, uint32_t& si, uint32_t& dr, uint32_t& di) {
  const uint32_t pr = hfnma(xi, ti, hmul(xr, tr)), pi = hfma(xi, tr, hmul(xr, ti));
  sr = hfnma(yi, ui, hfma(yr, ur, pr));
  si = hfma(yi, ur, hfma(yr, ui, pi));
  dr = hrefl(pr, sr);
  di = hrefl(pi, si);
}
template <int BH> __device__ __forceinline__ void fft_e1(const uint32_t (&d)[32], const uint32_t (&tw)[16], uint32_t (&a2)[2][2][4]) {
#pragma unroll
  for (int be = 0; be < 2; be++)
#pragma unroll
    for (int s = 0; s < 2; s++) {
      const int o = 16 * s + 8 * be + 2 * BH, p = 2 * BH;
      bfly(d[o], d[o + 1], tw[p], tw[p + 1], d[o + 4], d[o + 5], tw[p + 4], tw[p + 5], a2[be][0][s], a2[be][0][2 + s],
           a2[be][1][s], a2[be][1][2 + s]);
    }
}
__device__ __forceinline__ uint32_t hfms(uint32_t a, uint32_t b, uint32_t c) {
  uint32_t r;
  asm("{\n.reg .b32 t;\nneg.f16x2 t, %3;\nfma.rn.f16x2 %0, %1, %2, t;\n}\n" : "=r"(r) : "r"(a), "r"(b), "r"(c));
  return r;
}
template <int C, int J> __device__ __forceinline__ void fft_e2(const uint32_t (&d0)[8], const uint32_t (&d1)[8], uint32_t (&a3)[2][4]) {
  const uint32_t ur = d0[2 * J], ui = d0[4 + 2 * J], hr = d0[2 * J + 1], hi = d0[5 + 2 * J];
  const uint32_t vr = d1[2 * J], vi = d1[4 + 2 * J], gr = d1[2 * J + 1], gi = d1[5 + 2 * J];
  const uint32_t pr = hfnma(ui, hi, hmul(ur, hr)), pi = hfma(ui, hr, hmul(ur, hi));
  a3[0][2 + C] = pr;
  a3[0][C] = pi;
  a3[1][2 + C] = hfnma(vi, hi, hfma(vr, hr, hfnma(ui, gi, hfms(ur, gr, pi))));
  a3[1][C] = hfma(vi, hr, hfma(vr, hi, hfma(ui, gr, hfma(ur, gi, pr))));
}
__device__ __forceinline__ void fft_e3(const uint32_t (&d)[2][8], const uint32_t (&tw)[16], uint32_t zaddr) {
#pragma unroll
  for (int rho = 0; rho < 2; rho++) {
    uint32_t zr[4], zi[4];
#pragma unroll
    for (int nb = 0; nb < 4; nb++) {
      const uint32_t xi = d[nb >> 1][2 * (nb & 1) + rho], xr = d[nb >> 1][4 + 2 * (nb & 1) + rho];
      const uint32_t tr = tw[8 + 4 * rho + 2 * (nb & 1)], ti = tw[9 + 4 * rho + 2 * (nb & 1)];
      zr[nb] = hfnma(xi, ti, hmul(xr, tr));
      zi[nb] = hfma(xi, tr, hmul(xr, ti));
    }
    stsm4(zaddr + rho * 1024, zr[0], zr[1], zr[2], zr[3]);
    stsm4(zaddr + rho * 1024 + 512, zi[0], zi[1], zi[2], zi[3]);
  }
}
__device__ __forceinline__ float bf_lo(uint32_t v) {
  uint32_t r;
  asm("prmt.b32 %0, %1, 0, 0x1044;\n" : "=r"(r) : "r"(v));
  return __uint_as_float(r);
}
__device__ __forceinline__ float bf_hi(uint32_t v) { return __uint_as_float(v & 0xffff0000u); }
__device__ __forceinline__ float ex2(float x) {
  float r;
  asm("ex2.approx.ftz.f32 %0, %1;\n" : "=f"(r) : "f"(x));
  return r;
}
__device__ __forceinline__ float rcp(float x) {
  float r;
  asm("rcp.approx.ftz.f32 %0, %1;\n" : "=f"(r) : "f"(x));
  return r;
}

__device__ __forceinline__ int g2_a(int s) { return ((0xA1054 >> (4 * s)) & 15) * 16384; }
__device__ __forceinline__ int g2_b(int s) { return ((0xCDB32 >> (4 * s)) & 15) * 16384; }
static_assert(OFF_U == 10 * 16384 && OFF_H == 12 * 16384 && OFF_OP == 4 * 16384, "units");
__device__ __forceinline__ int g2_k(int hp, int i) {
  return i < 2 ? hp ^ 1 ^ i : i < 4 ? (hp & ~1) ^ i : ((hp & ~3) + i) & 15; }
__device__ __forceinline__ int y_slot(int wg, int it) {
  static_assert(T_B2 == T_TW + 8192 && T_A1 == T_B2 + 4096, "y slots");
  return OFF_T + T_TW + ((it + 3) & 3) * 4096 + wg * 2048;
}

__device__ __forceinline__ void to_arr(uint32_t (&d)[4], uint4 v) { d[0] = v.x; d[1] = v.y; d[2] = v.z; d[3] = v.w; }

__device__ __forceinline__ void attn_stage(uint32_t sb, int blk, int lane, const float (&acc)[96], uint32_t (&k1)[2][4]) {
  const int lr = lane & 7, lm = lane >> 3;
  const uint32_t base = sb + OFF_VP + (blk * 16 + lr + 8 * (lm & 1)) * 128;
#pragma unroll
  for (int i = 0; i < 8; i++) k1[i >> 2][i & 3] = pack_bf16(acc[34 + 4 * i], acc[35 + 4 * i]);
  const uint32_t kh = sb + OFF_KH + blk * 2048 + lane * 16;
  sts128(kh, k1[0][0], k1[0][1], k1[0][2], k1[0][3]);
  sts128(kh + 512, k1[1][0], k1[1][1], k1[1][2], k1[1][3]);
#pragma unroll
  for (int j = 0; j < 8; j += 2)
    stsm4(base + (((j + (lm >> 1)) ^ lr) << 4), pack_bf16(acc[64 + 4 * j], acc[65 + 4 * j]),
          pack_bf16(acc[66 + 4 * j], acc[67 + 4 * j]), pack_bf16(acc[68 + 4 * j], acc[69 + 4 * j]),
          pack_bf16(acc[70 + 4 * j], acc[71 + 4 * j]));
}
__device__ __forceinline__ void attn_pack(const float (&acc)[96], uint32_t (&qa)[2][8], uint32_t (&k0)[2][4]) {
#pragma unroll
  for (int hd = 0; hd < 2; hd++) {
#pragma unroll
    for (int i = 0; i < 8; i++) {
      asm volatile("cvt.rn.bf16x2.f32 %0, %1, %2;\n" : "=r"(qa[hd][i]) : "f"(acc[16 * hd + 2 * i + 1]), "f"(acc[16 * hd + 2 * i]));
    }
#pragma unroll
    for (int i = 0; i < 4; i++) {
      asm volatile("cvt.rn.bf16x2.f32 %0, %1, %2;\n" : "=r"(k0[hd][i]) : "f"(acc[33 + 16 * hd + 4 * i]), "f"(acc[32 + 16 * hd + 4 * i]));
    }
  }
}
__device__ __forceinline__ void pin8(bool p, float a, float b, float c, float d, float e, float f, float g, float h) {
  asm volatile("{\n.reg .pred p;\nsetp.ne.u32 p, %8, 0;\n@p st.volatile.shared.v4.f32 [%9], {%0,%1,%2,%3};\n@p st.volatile.shared.v4.f32 [%9], {%4,%5,%6,%7};\n}\n"
               ::"f"(a), "f"(b), "f"(c), "f"(d), "f"(e), "f"(f), "f"(g), "f"(h), "r"((uint32_t)p), "r"(0) : "memory");
}
__device__ __forceinline__ void pin8u(bool p, const uint32_t (&a)[8]) {
  asm volatile("{\n.reg .pred p;\nsetp.ne.u32 p, %8, 0;\n@p st.volatile.shared.v4.u32 [%9], {%0,%1,%2,%3};\n@p st.volatile.shared.v4.u32 [%9], {%4,%5,%6,%7};\n}\n"
               ::"r"(a[0]), "r"(a[1]), "r"(a[2]), "r"(a[3]), "r"(a[4]), "r"(a[5]), "r"(a[6]), "r"(a[7]), "r"((uint32_t)p), "r"(0) : "memory");
}
__device__ __forceinline__ void attn_own(const uint32_t (&k0)[2][4], const uint32_t (&k1)[2][4], bool le0, bool le1,
                                         const uint32_t (&qa)[2][8], float (&l)[2][4]) {
#pragma unroll
  for (int hd = 0; hd < 2; hd++) {
    float s0[4], s1[4];
    mma16816_z(s0, qa[hd][0], qa[hd][1], qa[hd][2], qa[hd][3], k0[hd][0], k0[hd][1]);
    mma16816_z(s1, qa[hd][0], qa[hd][1], qa[hd][2], qa[hd][3], k1[hd][0], k1[hd][1]);
    mma16816(s0, qa[hd][4], qa[hd][5], qa[hd][6], qa[hd][7], k0[hd][2], k0[hd][3]);
    mma16816(s1, qa[hd][4], qa[hd][5], qa[hd][6], qa[hd][7], k1[hd][2], k1[hd][3]);
    l[hd][0] = s0[0];
    l[hd][1] = s0[1];
    l[hd][2] = le0 ? s1[2] : s0[2];
    l[hd][3] = le1 ? s1[3] : s0[3];
  }
}
template <int N> __device__ __forceinline__ void quad_softmax(float (&x)[N][2], uint32_t (&pp)[N]) {
  const float c2 = 1.4426950408889634f;
  uint32_t q[N], mx[N / 2];
#pragma unroll
  for (int n = 0; n < N; n++) {
    const uint32_t r = pack_bf16(x[n][0], x[n][1]);
    q[n] = bfma2(r, 0x3e353e35u, bmul2(r, 0x379e379eu));
    x[n][0] = bf_lo(q[n]);
    x[n][1] = bf_hi(q[n]);
  }
#pragma unroll
  for (int n = 0; n < N / 2; n++)
    mx[n] = bmax2(__byte_perm(q[2 * n], q[2 * n + 1], 0x5410), __byte_perm(q[2 * n], q[2 * n + 1], 0x7632));
#pragma unroll
  for (int o = 1; o <= 2; o++)
#pragma unroll
    for (int n = 0; n < N / 2; n++) mx[n] = bmax2(mx[n], __shfl_xor_sync(0xffffffffu, mx[n], o));
  float m[N], t[N];
#pragma unroll
  for (int n = 0; n < N / 2; n++) {
    m[2 * n] = bf_lo(mx[n]);
    m[2 * n + 1] = bf_hi(mx[n]);
  }
#pragma unroll
  for (int n = 0; n < N; n++) {
    const float nm = -m[n] * c2;
    x[n][0] = ex2(fmaf(x[n][0], c2, nm));
    x[n][1] = ex2(fmaf(x[n][1], c2, nm));
    t[n] = x[n][0] + x[n][1];
  }
#pragma unroll
  for (int o = 1; o <= 2; o++)
#pragma unroll
    for (int n = 0; n < N; n++) t[n] += __shfl_xor_sync(0xffffffffu, t[n], o);
#pragma unroll
  for (int n = 0; n < N; n++) {
    const float inv = rcp(t[n]);
    pp[n] = pack_bf16(x[n][0] * inv, x[n][1] * inv);
  }
}
__device__ __forceinline__ void attn_pv(uint32_t dst, const uint32_t (&va)[4], const uint32_t (&vb)[4], uint32_t pp,
                                        uint32_t maskLE) {
  const uint32_t b0 = pp & ~maskLE, b1 = pp & maskLE;
  float oa[4], ob[4];
  mma16816_z(oa, va[0], va[1], va[2], va[3], b0, b1);
  mma16816_z(ob, vb[0], vb[1], vb[2], vb[3], b0, b1);
  stsm4t(dst, pack_bf16(oa[0], oa[1]), pack_bf16(oa[2], oa[3]), pack_bf16(ob[0], ob[1]), pack_bf16(ob[2], ob[3]));
}

template <int MODE>
__global__ void __cluster_dims__(2, 1, 1) __launch_bounds__(NTHREADS, 1)
fused_kernel(const Params p, const __grid_constant__ CUtensorMap tmX, const __grid_constant__ CUtensorMap tmW,
             const __grid_constant__ CUtensorMap tmWo,
             const __grid_constant__ CUtensorMap tmQ,
             const __grid_constant__ CUtensorMap tmXh, const __grid_constant__ CUtensorMap tmWh) {
  extern __shared__ __align__(1024) uint8_t smem[];
  const uint32_t sb = smem_u32(smem) - OFF_L0;
  const uint32_t bars = sb + OFF_BAR;
  const int tid = threadIdx.x, lane = tid & 31, warp = __shfl_sync(0xffffffffu, tid >> 5, 0);
  const int rank = blockIdx.x & 1;
  const bool halo_cta = blockIdx.x < 4;
  if (halo_cta && MODE != 0) return;
  int grp, mem;
  {
    const int t = (blockIdx.x >> 1) - 4, u = t - 32;
    const int q7 = (u * 37) >> 8;
    const bool lo = (unsigned)t < 32u, mid = (unsigned)u < 28u;
    grp = lo ? (t & 7) : (mid ? 1 + u - 7 * q7 : 0);
    mem = lo ? (t >> 3) : (mid ? 4 + q7 : (t < 0 ? t + 6 : t - 54));
  }
  const int rg = (grp >> 2) * 4 + (mem >> 1), hp = (grp & 3) * 4 + (mem & 1) * 2 + rank;
  const int rb2 = (grp >> 2) * 8 + mem, cb2 = (grp & 3) * 2 + rank;
  const int chb = grp * 16 + mem * 2 + rank;
  const int cta = rg * 16 + hp;
  const int par = rg >> 2, gidx = rg & 3;

  if (tid < 256 && !halo_cta && MODE != 2) {
    const int r = tid >> 3, c = tid & 7;
    const uint32_t so = r * 128 + ((c ^ (r & 7)) << 4);
    const __nv_bfloat16* wg0 = p.w + (size_t)r * (3 * DM) + hp * 64 + c * 8;
    const __nv_bfloat16* xg0 = p.x + (size_t)(2 * (gidx * 256 + r) + par) * DM + c * 8;
#pragma unroll
    for (int j = 0; j < 3; j++) cp_async16n(sb + OFF_1B + j * 4096 + so, wg0 + j * DM);
#pragma unroll
    for (int i = 0; i < 8; i++) cp_async16n(sb + i * 4096 + so, xg0 + (size_t)i * 64 * DM);
    asm volatile("cp.async.commit_group;\n" ::: "memory");
  }
  if (tid == 256) {
    prefetch_tmap(halo_cta ? &tmXh : &tmX);
#pragma unroll
    for (int i = 0; i < NS1B; i++) mbar_init(bars + 8 * (BAR_FULLB + i), 1);
#pragma unroll
    for (int i = 0; i < NS1A; i++) mbar_init(bars + 8 * (BAR_FULLA + i), 1);
    asm volatile("fence.mbarrier_init.release.cluster;\n" ::: "memory");
    if (!halo_cta && MODE != 2) {
      mbar_expect_tx(bars + 8 * (BAR_FULLB + 1), STG1B);
      tma_load_3d(sb + OFF_1B + 1 * STG1B, &tmW, bars + 8 * (BAR_FULLB + 1), hp * 64, 32, 0);
      mbar_expect_tx(bars + 8 * (BAR_FULLB + 2), STG1B);
      tma_load_3d(sb + OFF_1B + 2 * STG1B, &tmW, bars + 8 * (BAR_FULLB + 2), hp * 64, 64, 0);
    } else {
      prefetch_tmap(&tmWh);
    }
  } else if (tid == 288) {
#pragma unroll
    for (int i = 0; i < NS1A; i++) mbar_init(bars + 8 * (BAR_EMPTYA + i), 4);
#pragma unroll
    for (int i = 0; i < NS1B; i++) mbar_init(bars + 8 * (BAR_EMPTYB + i), 2);
    asm volatile("fence.mbarrier_init.release.cluster;\n" ::: "memory");
  } else if (tid == 320) {
#pragma unroll
    for (int i = 0; i < NS2; i++) {
      mbar_init(bars + 8 * (BAR_FULL2 + i), 1);
      mbar_init(bars + 8 * (BAR_EMPTY2 + i), 4);
    }
    mbar_init(bars + 8 * BAR_DEAD, 2);
    mbar_init(bars + 8 * (BAR_DEAD + 1), 2);
    mbar_init(bars + 8 * BAR_X, 2);
    mbar_init(bars + 8 * BAR_REL, 2);
    asm volatile("fence.mbarrier_init.release.cluster;\n" ::: "memory");
  } else if (tid == 352) {
    mbar_init(bars + 8 * BAR_T, 1);
    mbar_init(bars + 8 * BAR_UH, 3);
    mbar_init(bars + 8 * BAR_LFREE, 4);
    mbar_init(bars + 8 * BAR_LAND, 1);
    mbar_init(bars + 8 * BAR_U, 1);
    mbar_init(bars + 8 * BAR_Q, 1);
    mbar_init(bars + 8 * BAR_STG, 9);
    asm volatile("fence.mbarrier_init.release.cluster;\n" ::: "memory");
  }
  if (warp == 8) PROF2(23);
  cluster_sync_all();
  if (warp == 8) PROF2(24);

  if (warp >= 8) {
    const int hw = warp - 8;
    const int lr = lane & 7, lm = lane >> 3;
    auto g1_issue_a = [&](int j, int s) {
      const uint32_t fb = bars + 8 * (BAR_FULLA + s);
      mbar_expect_tx(fb, STG1A);
      tma_load_3d_mc(sb + s * STG1A + rank * 16384, &tmX, fb, j * 64, par, gidx * 256 + rank * 128);
    };
    auto g1_issue_b = [&](int kb, int s) {
      const uint32_t fb = bars + 8 * (BAR_FULLB + s);
      mbar_expect_tx(fb, STG1B);
      tma_load_3d(sb + OFF_1B + s * STG1B, &tmW, fb, hp * 64, kb * 32, 0);
    };
    asm volatile("setmaxnreg.dec.sync.aligned.u32 %0;\n" :: "n"(REG_HELP));

    if (halo_cta) {
      if (hw == 0) {
        int s = 0, ph = 1;
#pragma unroll 1
        for (int kb = 0; kb < 16; kb++) {
          mbar_wait(bars + 8 * (BAR_EMPTYB + s), ph);
          const uint32_t fb = bars + 8 * (BAR_FULLB + s), st = sb + s * STGH;
          if (elect_one()) {
            mbar_expect_tx(fb, STGH);
            tma_load_4d(st, &tmXh, fb, kb * 64, 248, 0, 0);
            tma_load_3d(st + 8192, &tmWh, fb, 0, kb * 64, 16 + blockIdx.x * 4);
            tma_load_3d(st + 8192 + 32768, &tmWh, fb, 0, kb * 64, 32 + blockIdx.x * 4);
          }
          if (++s == 3) { s = 0; ph ^= 1; }
        }
      }
      __syncwarp();
    } else if (hw == 0) {
      uint32_t epoch = 0;
      if (lane < (MODE == 2 ? NS2 : 2)) mbar_arrive_cluster_n(mapa(bars, rank) + 8 * (BAR_EMPTY2 + lane), 4);
      if (MODE != 2) {
      epoch = ld_relaxed(g_flag_o + 2 * cta) + 1;
      if (lane == 0) {
        mbar_expect_tx(bars + 8 * BAR_U, 32768);
        mbar_expect_tx(bars + 8 * BAR_LAND, 32768 + 64);
        mbar_expect_tx(bars + 8 * BAR_Q, 32768);
        mbar_expect_tx(bars + 8 * BAR_T, T_END);
      }
      {
        int sa = 1, pha = 1, sbb = 2, phb = 1;
#pragma unroll 1
        for (int kb = 2; kb < 32; kb++) {
          if (!(kb & 1)) {
            mbar_wait(bars + 8 * (BAR_EMPTYA + sa), pha);
            if (elect_one()) g1_issue_a(kb >> 1, sa);
            if (++sa == NS1A) { sa = 0; pha ^= 1; }
          }
          mbar_wait(bars + 8 * (BAR_EMPTYB + sbb), phb);
          if (kb > 2 && elect_one()) g1_issue_b(kb, sbb);
          __syncwarp();
          if (kb >= PF0 && kb < PF0 + 12)
            prefetch_l2((kb < PF0 + 8 ? p.q + (size_t)chb * 16384 + (kb - PF0) * 2048 : p.wo + (size_t)chb * 8192 + (kb - PF0 - 8) * 2048) + lane * 64);
          if (kb == 4) PROF2(27);
          if (kb == 1) PROF2(38);
          if (kb == 2) PROF2(39);
          if (++sbb == NS1B) { sbb = 0; phb ^= 1; }
        }
      }
      static_assert(32 % NS1B == 2 && (32 / NS1B) % 2 == 0 && OFF_Q == OFF_1B && 2 * STG1B == 6 * 4096, "slots / parity of these loads");
      const uint8_t* tab = reinterpret_cast<const uint8_t*>(g_tab);
      if (lane == 0) {
        prefetch_tmap(&tmWo);
        prefetch_tmap(&tmQ);
        bulk_load(sb + OFF_T + T_A1, tab + T_A1, T_END - T_A1, bars + 8 * BAR_T);
        mbar_wait(bars + 8 * (BAR_EMPTYB + 2), 1);
        tma_load_5d(sb + OFF_Q + 6 * 4096, &tmQ, bars + 8 * BAR_Q, (chb & ~1) * 8, rank * 32 + 24);
        tma_load_5d(sb + OFF_Q + 7 * 4096, &tmQ, bars + 8 * BAR_Q, (chb & ~1) * 8, rank * 32 + 28);
        if (gidx != 0) wait_flag(g_flag_h + (hp >> 2), epoch);
      }
      __syncwarp();
      {
        uint4 hk0 = make_uint4(0, 0, 0, 0), hk1 = hk0, hv0 = hk0, hv1 = hk0;
        if (gidx != 0) {
          const uint4* src = g_halo + cta * 128 + lane;
          hk0 = __ldcg(src); hk1 = __ldcg(src + 32); hv0 = __ldcg(src + 64); hv1 = __ldcg(src + 96);
        }
        if (lane == 0) {
          mbar_wait(bars + 8 * (BAR_EMPTYB + 3), 1);
          bulk_load(sb + OFF_T, tab, T_TW, bars + 8 * BAR_T);
        }
        __syncwarp();
        PROF2(18);
        sts128(sb + OFF_L0 + lane * 16, hk0.x, hk0.y, hk0.z, hk0.w);
        sts128(sb + OFF_L0 + 512 + lane * 16, hk1.x, hk1.y, hk1.z, hk1.w);
        stsm4(sb + OFF_L0 + 1024 + lr * 128 + ((lm ^ lr) << 4), hv0.x, hv0.y, hv0.z, hv0.w);
        stsm4(sb + OFF_L0 + 1024 + lr * 128 + (((4 + lm) ^ lr) << 4), hv1.x, hv1.y, hv1.z, hv1.w);
        __syncwarp();
        if (lane == 0) {
          mbar_arrive(bars + 8 * BAR_STG);
          mbar_wait(bars + 8 * (BAR_EMPTYB + 4), 1);
          bulk_load(sb + OFF_T + T_TW, tab + T_TW, T_A1 - T_TW, bars + 8 * BAR_T);
          mbar_wait(bars + 8 * BAR_EMPTYB, 0);
#pragma unroll 1
          for (int i = 0; i < 6; i++) tma_load_5d(sb + OFF_Q + i * 4096, &tmQ, bars + 8 * BAR_Q, (chb & ~1) * 8, rank * 32 + i * 4);
        }
        __syncwarp();
      }
      }
      if (MODE != 1) {
        auto korder = [&](int i) { return MODE == 2 ? i : g2_k(hp, i); };
        const __nv_bfloat16* osrc = g_o + (size_t)(rb2 >> 1) * 16 * 16384 + ((rb2 & 1) * 2 + rank) * 4096;
        const uint32_t* flag = g_flag_o + (rb2 >> 1) * 32 + korder(lane & 15) * 2 + (rb2 & 1);
        uint32_t ready = MODE == 0 ? 0u : ~0u, pv = 0;
        auto look = [&]() {
          ready |= __ballot_sync(0xffffffffu, pv == epoch);
          asm volatile("fence.acquire.gpu;\n" ::: "memory");
          fence_async_all();
        };
        if (MODE == 0) {
          mbar_wait_idle(bars + 8 * BAR_REL, 0);
          if (POLL1) pv = ld_relaxed(flag);
          if (elect_one()) {
            mbar_expect_tx(bars + 8 * BAR_FULL2, STG2);
            tma_load_3d(sb + g2_b(0), &tmWo, bars + 8 * BAR_FULL2, 0, korder(0) * 64, cb2 * 2);
            tma_load_3d(sb + g2_b(1), &tmWo, bars + 8 * (BAR_FULL2 + 1), 0, korder(1) * 64, cb2 * 2);
          }
          if (POLL1) look();
        }
#pragma unroll
        for (int i = MODE == 0 ? 2 : 0; i < 16; i++) {
          const int kb = korder(i), s = i % NS2, ph = (i / NS2) & 1;
          const uint32_t fb = bars + 8 * (BAR_FULL2 + s);
          if (!((ready >> i) & 1)) {
            int n = 0;
            do {
              ready |= __ballot_sync(0xffffffffu, ld_acquire(flag) == epoch);
            } while (!((ready >> i) & 1) && ++n < SPIN_LIMIT);
            fence_async_all();
          }
          if (i == 2) PROF(21);
          mbar_wait(bars + 8 * (BAR_EMPTY2 + s), ph);
          if (elect_one()) {
            mbar_expect_tx(fb, STG2);
            asm volatile(
                "cp.async.bulk.shared::cluster.global.mbarrier::complete_tx::bytes.multicast::cluster [%0], [%1], %2, [%3], %4;\n"
                ::"r"(sb + g2_a(s) + rank * 8192), "l"(osrc + kb * 16384), "r"(8192), "r"(fb), "h"((uint16_t)3) : "memory");
            if (MODE != 0 || i >= 4) tma_load_3d(sb + g2_b(s), &tmWo, fb, 0, kb * 64, cb2 * 2);
          }
          if (MODE == 0 && i == LA0) pv = ld_relaxed(flag);
          if (MODE == 0 && i == LA1) look();
          if (i == 3) PROF(37);

        }
      }
      __syncwarp();
    } else if (MODE != 2) {
      {
        const int g = lane >> 2, t = lane & 3;
        uint32_t w[2][4];
#pragma unroll
        for (int h = 0; h < 2; h++) {
          const uint2 x = __ldg(reinterpret_cast<const uint2*>(p.shift_k + ((chb & ~1) * 8 + h * 8 + g) * 4));
          w[h][0] = __byte_perm(x.x, x.x, 0x1010);
          w[h][1] = __byte_perm(x.x, x.x, 0x3232);
          w[h][2] = __byte_perm(x.y, x.y, 0x1010);
          w[h][3] = __byte_perm(x.y, x.y, 0x3232);
        }
        auto swz = [](int r) { return (((r & 29) | ((r ^ (r >> 2)) & 2)) << 5) | (r & 16); };
        const uint32_t kring = sb + OFF_H + (hw - 1) * 8192, vring = kring + 4096;
        const int s0 = rank * 32 + (hw - 1) * 11, s1 = hw == 3 ? rank * 32 + 32 : s0 + 11;
        const size_t goff = (size_t)(lane >> 1) * DM + (chb & ~1) * 8 + (lane & 1) * 8;
        const __nv_bfloat16* kg = p.k + goff;
        const __nv_bfloat16* vg = p.v + goff;
        const uint32_t d0 = swz(lane >> 1) ^ ((lane & 1) << 4), d1 = swz(16 + (lane >> 1)) ^ ((lane & 1) << 4);
        auto issue = [&](int st) {
          const uint32_t so = (st & 3) << 10;
          cp_async16(kring + so + d0, kg + (size_t)st * 32 * DM, 16);
          cp_async16(kring + so + d1, kg + (size_t)(st * 32 + 16) * DM, 16);
          cp_async16(vring + so + d0, vg + (size_t)st * 32 * DM, 16);
          cp_async16(vring + so + d1, vg + (size_t)(st * 32 + 16) * DM, 16);
        };
        const int xa = 8 * (lr >> 1) + 2 * lm + (lr & 1), xb = 8 * (lr >> 1) - 4 + 2 * (lm & 1) + (lr & 1);
        const uint32_t la = swz(xa), lb = swz(xb & 31);
        const int backb = xb < 0 ? 1 : 0;
        const uint32_t ud[2] = {mapa(sb + OFF_U + g * 4096 + t * 16, 0), mapa(sb + OFF_U + g * 4096 + t * 16, 1)};
        const uint32_t ub[2] = {mapa(bars + 8 * BAR_U, 0), mapa(bars + 8 * BAR_U, 1)};
        if (lane == 0) mbar_wait(bars + 8 * (BAR_FULLB + NS1B - 1), 0);
        __syncwarp();
        if (lane >= 24) cp_async16(kring + (((s0 - 1) & 3) << 10) + d1, s0 > 0 ? kg + (size_t)(s0 * 32 - 16) * DM : kg, s0 > 0 ? 16 : 0);
        issue(s0);
        asm volatile("cp.async.commit_group;\n" ::: "memory");
        issue(s0 + 1);
        asm volatile("cp.async.commit_group;\n" ::: "memory");
#pragma unroll 1
        for (int st = s0; st < s1; st++) {
          if (st + 2 < s1) issue(st + 2);
          if (hw == 1 && st - s0 < 8) prefetch_l2(p.ssm_k + (size_t)(chb * 8 + st - s0) * SEQ + lane * 64);
          if (hw == 2 && st == s0 + 4 && lane < 2) prefetch_l2(g_tab + (chb * 2 + lane) * 32);
          const uint32_t uo = (st ^ ((g ^ (st >> 2)) & 1)) * 64;
          asm volatile("cp.async.commit_group;\n" ::: "memory");
          asm volatile("cp.async.wait_group 2;\n" ::: "memory");
          __syncwarp();
#pragma unroll
          for (int h = 0; h < 2; h++) {
            uint32_t e[6], vv[4], e4[4];
            ldsm4t(e4, kring + ((st & 3) << 10) + (la ^ (h << 4)));
            ldsm2t(e[0], e[1], kring + (((st - backb) & 3) << 10) + (lb ^ (h << 4)));
            ldsm4t(vv, vring + ((st & 3) << 10) + (la ^ (h << 4)));
            e[2] = e4[0]; e[3] = e4[1]; e[4] = e4[2]; e[5] = e4[3];
            uint32_t o[5];
#pragma unroll
            for (int i = 0; i < 5; i++) o[i] = __byte_perm(e[i], e[i + 1], 0x5432);
#pragma unroll
            for (int i = 0; i < 4; i++) {
              uint32_t a = bmul2(o[i], w[h][3]);
              a = bfma2(e[i + 1], w[h][2], a);
              a = bfma2(o[i + 1], w[h][1], a);
              a = bfma2(e[i + 2], w[h][0], a);
              vv[i] = bmul2(a, vv[i]);
            }
            st_async128(ud[h] + uo, ub[h], vv[0], vv[1], vv[2], vv[3]);
          }
          __syncwarp();
        }
        PROF(16);
      }
      {
        const int rw = (lane >> 3) + (lane & 4), ck = lane & 3;
        const uint32_t so = rw * 64 + ck * 16, dof = rw * 128 + ((ck ^ rw) << 4);
        const uint8_t* hsrc = reinterpret_cast<const uint8_t*>(p.ssm_k + (size_t)chb * 8 * SEQ) + so;
        const float dv = lane < 8 ? __bfloat162float(p.ssm_D[chb * 8 + lane]) : 0.f;
        uint32_t x[32];
        auto load = [&](const uint8_t* src, int i) {
          asm volatile("ld.v4.u32 {%0,%1,%2,%3}, [%4];\n" : "=r"(x[4 * i]), "=r"(x[4 * i + 1]), "=r"(x[4 * i + 2]), "=r"(x[4 * i + 3])
                       : "l"(src + i * 512) : "memory");
        };
#pragma unroll
        for (int i = 0; i < 8; i++) load(hsrc + (hw - 1) * 4096, i);
        nb_sync(NB_HELP3, 96);
        mbar_wait(bars + 8 * BAR_U, 0);
        int eh = 0;
#pragma unroll 1
        for (int n = 2 * (hw - 1); n < 16; n += (n & 1) ? 5 : 1) {
          const int c = n >> 1;
          const uint8_t* nsrc = (n & 1) ? hsrc + (c < 5 ? c + 3 : c) * 4096
                                        : smem - OFF_L0 + OFF_U + c * 4096 + (so ^ (((c ^ (lane >> 2)) & 1) << 6));
          const uint32_t dst = sb + ((n & 1) ? OFF_U : OFF_H) + c * 4096 + dof;
          const float dc = __shfl_sync(0xffffffffu, dv, c);
          const float h0 = bf_lo(x[0]) + ((lane | (n & 1)) == 0 ? dc : 0.f), h1 = bf_hi(x[0]);
          x[0] = pack_bf16(h0, h1);
          uint32_t m[2] = {x[0], x[1]};
#pragma unroll
          for (int i = 2; i < 32; i++) asm("max.xorsign.abs.bf16x2 %0, %0, %1;\n" : "+r"(m[i & 1]) : "r"(x[i]));
          asm("max.xorsign.abs.bf16x2 %0, %0, %1;\n" : "+r"(m[0]) : "r"(m[1]));
          const uint32_t e = max(__reduce_max_sync(0xffffffffu, max((m[0] >> 7) & 255u, (m[0] >> 23) & 255u)), 5u);
          const uint32_t sc = (259u - e) * 0x00800080u;
#pragma unroll
          for (int i = 0; i < 8; i++) {
            uint32_t o[4];
#pragma unroll
            for (int j = 0; j < 4; j++) {
              const uint32_t v = bmul2(x[4 * i + j], sc);
              asm("cvt.rn.f16x2.f32 %0, %1, %2;\n" : "=r"(o[j]) : "f"(bf_hi(v)), "f"(i + j == 0 ? h0 * bf_hi(sc) : bf_lo(v)));
            }
            sts128((dst + (i & 3) * 1024) ^ ((i >> 2) << 6), o[0], o[1], o[2], o[3]);
            load(nsrc, i);
          }
          if (n & 1) {
            const int f = min(max((int)e + eh - 129, 0), 254);
            if (lane < 2)
              asm volatile("st.async.weak.shared::cluster.mbarrier::complete_tx::bytes.b32 [%0], %2, [%1];\n"
                           ::"r"(mapa(sb + OFF_SC + rank * 32 + c * 4, lane)), "r"(mapa(bars + 8 * BAR_LAND, lane)), "r"(f << 7) : "memory");
          }
          eh = e;
        }
        fence_async_smem();
        __syncwarp();
        if (lane == 0) mbar_arrive(bars + 8 * BAR_UH);
        PROF(32);
      }
      if (hw < 3) {
        const uint32_t rb = mapa(bars, lane & 1);
        const uint32_t epoch = ld_relaxed(g_flag_o + 2 * cta + hw - 1) + 1;
        const bool own = hw - 1 == (rb2 & 1);
        nb_sync(NB_OREADY + hw - 1, 160);
        if (lane == 0) {
          asm volatile("cp.async.bulk.global.shared::cta.bulk_group [%0], [%1], %2;\n" ::"l"(g_o + (size_t)cta * 16384 + (hw - 1) * 8192),
                       "r"(sb + OFF_OP + (own ? 16384 : 0)), "r"(16384) : "memory");
          bulk_commit();
        }
        if (lane < 2) {
          mbar_arrive_cluster(rb + 8 * (BAR_EMPTY2 + 2));
          mbar_arrive_cluster(rb + 8 * (BAR_EMPTY2 + 3));
        }
        if (lane == 0) {
          bulk_wait0();
          if (own) mbar_expect_tx(bars + 8 * (BAR_FULL2 + 1), 16384);
          mbar_arrive_cluster(mapa(bars, own ? rank : rank ^ 1) + 8 * BAR_X);
          st_release(g_flag_o + 2 * cta + hw - 1, epoch);
          mbar_arrive(bars + 8 * BAR_REL);
        }
        __syncwarp();
        PROF(own ? 17 : 19);
      } else {
        if (MODE == 0) {
          mbar_wait_idle(bars + 8 * BAR_X, 0);
          if (elect_one())
            asm volatile("cp.async.bulk.shared::cluster.shared::cta.mbarrier::complete_tx::bytes [%0], [%1], %2, [%3];\n"
                         ::"r"(mapa(sb + OFF_OP, rank ^ 1)), "r"(sb + OFF_OP + 16384), "r"(16384),
                         "r"(mapa(bars + 8 * BAR_FULL2, rank ^ 1)) : "memory");
        }
        if (MODE == 0) {
          mbar_wait_idle(bars + 8 * BAR_DEAD, 0);
          if (elect_one()) {
            tma_load_3d(sb + g2_b(2), &tmWo, bars + 8 * (BAR_FULL2 + 2), 0, g2_k(hp, 2) * 64, cb2 * 2);
            tma_load_3d(sb + g2_b(3), &tmWo, bars + 8 * (BAR_FULL2 + 3), 0, g2_k(hp, 3) * 64, cb2 * 2);
          }
        }
        __syncwarp();
      }
      {
        const int c8 = (4 * (lr >> 1) + 2 * (lm & 1) + (lr & 1)) & 7;
        const bool own = (lr >> 2) == rank;
        const uint32_t ya = sb + (own ? y_slot(c8 & 1, c8 >> 1) : OFF_LAND + c8 * 2048);
        const uint32_t yx = ((lm >> 1) ^ lr) << 4;
        const int row = (lane >> 4) * 8 + ((lane >> 3) & 1) * 16 + ((lane >> 2) & 1);
        uint2* og = reinterpret_cast<uint2*>(p.out + (size_t)(rank * 1024 + row) * (2 * DM) + (chb & ~1) * 8 + (lane & 3) * 4);
        const uint32_t qa = sb + OFF_Q + (lane >> 4) * 512 + (lane & 15) * 8;
        mbar_wait(bars + 8 * BAR_Q, 0);
        mbar_wait_idle(bars + 8 * BAR_LAND, 0);
        PROF(33);
        const uint32_t t0 = clock();
        const uint4 s4 = lds128(sb + OFF_SC + (lane & 3) * 16);
        const uint32_t sc[2] = {s4.x | (s4.y << 16), s4.z | (s4.w << 16)};
        auto fin = [&](uint32_t q2, uint32_t y2, uint32_t s2) {
          float lo, hi;
          asm("{\n.reg .b16 l, h;\nmov.b32 {l, h}, %2;\ncvt.f32.f16 %0, l;\ncvt.f32.f16 %1, h;\n}\n" : "=f"(lo), "=f"(hi) : "r"(y2));
          return bmul2(q2, bmul2(pack_bf16(lo, hi), s2));
        };
#pragma unroll 1
        for (int j = hw - 1; j < 16; j += 3) {
          uint32_t y[4][4];
          uint2 q[8];
          while ((uint32_t)clock() - t0 < j * PACE) __nanosleep(40);
          const uint32_t qj = qa + j * 2048;
#pragma unroll
          for (int i = 0; i < 4; i++) ldsm4t(y[i], ya + j * 128 + (yx ^ (i << 5)));
#pragma unroll
          for (int i = 0; i < 8; i++) q[i] = lds64(qj + (i >> 2) * 1024 + (i & 3) * 128);
#pragma unroll
          for (int i = 0; i < 8; i++) {
            og[(size_t)(j * 64 + (i >> 2) * 32 + (i & 3) * 2) * (2 * DM / 4)] =
                make_uint2(fin(q[i].x, y[i >> 1][2 * (i & 1)], sc[0]), fin(q[i].y, y[i >> 1][2 * (i & 1) + 1], sc[1]));
            if (i < 7) asm volatile("nanosleep.u32 %0;\n" ::"r"(FINE) : "memory");
          }
        }
      }
      PROF(22);
    }
    cluster_sync_all();
  } else {
    asm volatile("setmaxnreg.inc.sync.aligned.u32 %0;\n" :: "n"(REG_MATH));
    if (warp == 0) PROF2(26);
    const int wg = warp >> 2;
    const int wtid = tid & 127;
    const bool signaller = (wtid == 0) || (wtid == 32);
    const uint32_t rbars = mapa(bars, wtid >> 5 & 1);

    if (halo_cta) {
      const uint32_t epoch = ld_relaxed(g_flag_h + blockIdx.x) + 1;
      float acc0[64], acc1[64];
      int s = 0, ph = 0;
#pragma unroll 1
      for (int kb = 0; kb < 16; kb++) {
        mbar_wait(bars + 8 * (BAR_FULLB + s), ph);
        const uint32_t st = sb + s * STGH;
        const uint64_t da = mkdesc(st, 16, 1024, 1);
        const uint64_t db = mkdesc(st + 8192 + wg * 32768, 8192, 1024, 1);
        wg_fence();
#pragma unroll
        for (int kk = 0; kk < 4; kk++) {
          wgmma_n128(acc0, da + 2 * kk, db + 128 * kk, kb + kk);
          wgmma_n128(acc1, da + 2 * kk, db + 1024 + 128 * kk, kb + kk);
        }
        wg_commit();
        wg_wait<0>();
        if (wtid == 0) mbar_arrive(bars + 8 * (BAR_EMPTYB + s));
        if (++s == 3) { s = 0; ph ^= 1; }
      }
      fence_regs(acc0);
      fence_regs(acc1);
      if ((warp & 3) != 3) {
#pragma unroll
        for (int hh = 0; hh < 2; hh++) {
          uint4* dst = g_halo + ((hh * 4 + (warp & 3) + 1) * 16 + blockIdx.x * 4) * 128 + wg * 64 + lane;
#pragma unroll
          for (int j = 0; j < 4; j++) {
            const int o = 16 * j + 2 * hh;
            dst[(j >> 1) * 128 + (j & 1) * 32] =
                make_uint4(pack_bf16(acc0[o], acc0[o + 1]), pack_bf16(acc0[o + 4], acc0[o + 5]),
                           pack_bf16(acc0[o + 8], acc0[o + 9]), pack_bf16(acc0[o + 12], acc0[o + 13]));
            dst[(2 + (j >> 1)) * 128 + (j & 1) * 32] =
                make_uint4(pack_bf16(acc1[o], acc1[o + 1]), pack_bf16(acc1[o + 4], acc1[o + 5]),
                           pack_bf16(acc1[o + 8], acc1[o + 9]), pack_bf16(acc1[o + 12], acc1[o + 13]));
          }
        }
      }
      nb_sync(NB_G1DONE, 256);
      if (tid == 0) st_release(g_flag_h + blockIdx.x, epoch);
      PROF(36);
      cluster_sync_all();
      return;
    }

    float acc[64];
    auto g2_step = [&](int s, int kb) {
      const uint64_t da = mkdesc(sb + g2_a(s) + wg * 8192, 16, 1024, 1);
      const uint64_t db = mkdesc(sb + g2_b(s), 8192, 1024, 1);
      wg_fence();
      wgmma_n128(acc, da, db, kb);
      wgmma_n128(acc, da + 2, db + 128, 1);
      wgmma_n128(acc, da + 4, db + 256, 1);
      wgmma_n128(acc, da + 6, db + 384, 1);
      wg_commit();
    };

    if (MODE != 2) {
    uint32_t a1[2][4], tw[16], d1[32];
    const uint32_t tb = sb + OFF_T + wtid * 16;
    const uint64_t dx = mkdesc(sb + OFF_U + wg * 4096, OFF_H - OFF_U, 1024, 1);
    auto s1 = [&](int it) {
      hmma_n128t<0>(d1, a1[0], dx + it * 512);
      hmma_n128t<1>(d1, a1[1], dx + it * 512 + 128);
      wg_commit();
    };
    auto ldtw = [&](int i) {
      const uint4 v = lds128(tb + T_TW + i * 2048);
      tw[4 * i] = v.x; tw[4 * i + 1] = v.y; tw[4 * i + 2] = v.z; tw[4 * i + 3] = v.w;
    };
    {
      float acc0[96], acc1[96];
      int sa = 0, pha = 0, sbb = 0, phb = 0;
      asm volatile("cp.async.wait_group 0;\n" ::: "memory");
      fence_async_smem();
      nb_sync(NB_FIRST, 256);
      if (tid == 0) {
        mbar_arrive(bars + 8 * BAR_FULLA);
        mbar_arrive(bars + 8 * BAR_FULLB);
      }
      PROF(0 + wg);
#pragma unroll 1
      for (int kb = 0; kb < 30; kb++) {
        if (!(kb & 1)) mbar_wait(bars + 8 * (BAR_FULLA + sa), pha);
        mbar_wait(bars + 8 * (BAR_FULLB + sbb), phb);
        if (kb == 0) PROF2(0 + wg);
        if (kb == 4 && wg == 0) PROF2(28);
        if (kb == 8 && wg == 0) PROF2(29);
        if (kb == 16 && wg == 0) PROF2(30);
        const uint64_t da = mkdesc(sb + sa * STG1A + wg * 16384 + (kb & 1) * 64, 16, 1024, 1);
        const uint64_t db = mkdesc(sb + OFF_1B + sbb * STG1B, 4096, 1024, 1);
        wg_fence();
        wgmma_n192(acc0, da, db, kb);
        wgmma_n192(acc1, da + 512, db, kb);
        wgmma_n192(acc0, da + 2, db + 128, 1);
        wgmma_n192(acc1, da + 514, db + 128, 1);
        wg_commit();
        wg_wait<1>();
        if (kb > 0) {
          if (wtid == 64) mbar_arrive(bars + 8 * (BAR_EMPTYB + (sbb == 0 ? NS1B - 1 : sbb - 1)));
          if (!(kb & 1) && signaller) mbar_arrive_cluster(rbars + 8 * (BAR_EMPTYA + (sa == 0 ? NS1A - 1 : sa - 1)));
        }
        if (++sbb == NS1B) { sbb = 0; phb ^= 1; }
        if ((kb & 1) && ++sa == NS1A) { sa = 0; pha ^= 1; }
      }
      const int blk0 = wg * 8 + (warp & 3);
      const int lr = lane & 7, lm = lane >> 3;
      const bool le0 = 2 * (lane & 3) <= (lane >> 2), le1 = 2 * (lane & 3) + 1 <= (lane >> 2);
      const uint32_t maskLE = (le0 ? 0x0000FFFFu : 0u) | (le1 ? 0xFFFF0000u : 0u);
      uint32_t k0[2][2][4], k1[2][2][4], qa[2][2][8];
      float l[2][2][4];
      {
        static_assert(15 % NS1A == 0 && 30 % NS1B == 0, "slots of the last k blocks");
        mbar_wait(bars + 8 * BAR_FULLA, 1);
        mbar_wait(bars + 8 * BAR_FULLB, 0);
        mbar_wait(bars + 8 * (BAR_FULLB + 1), 0);
        const uint64_t da = mkdesc(sb + wg * 16384, 16, 1024, 1);
        const uint64_t db = mkdesc(sb + OFF_1B, 4096, 1024, 1);
        wg_fence();
#pragma unroll
        for (int i = 0; i < 4; i++) wgmma_n192(acc0, da + 2 * i, db + (i >> 1) * (STG1B >> 4) + (i & 1) * 128, 1);
        wg_commit();
        wg_wait<1>();
        if (wtid == 64) mbar_arrive(bars + 8 * (BAR_EMPTYB + NS1B - 1));
#pragma unroll
        for (int i = 0; i < 2; i++) wgmma_n192(acc1, da + 512 + 2 * i, db + (i >> 1) * (STG1B >> 4) + (i & 1) * 128, 1);
        wg_commit();
        wg_wait<1>();
        fence_regs(acc0);
        attn_stage(sb, blk0, lane, acc0, k1[0]);
#pragma unroll
        for (int i = 2; i < 4; i++) wgmma_n192(acc1, da + 512 + 2 * i, db + (i >> 1) * (STG1B >> 4) + (i & 1) * 128, 1);
        wg_commit();
        attn_pack(acc0, qa[0], k0[0]);
        wg_wait<0>();
        fence_regs(acc1);
      }
      if (wtid == 64) mbar_arrive(bars + 8 * BAR_EMPTYB);
      PROF(2 + wg);
      attn_stage(sb, blk0 + 4, lane, acc1, k1[1]);
      __syncwarp();
      if (lane == 0) mbar_arrive(bars + 8 * BAR_STG);
      mbar_wait(bars + 8 * BAR_U, 0);
      attn_pack(acc1, qa[1], k0[1]);
      attn_own(k0[0], k1[0], le0, le1, qa[0], l[0]);
      attn_own(k0[1], k1[1], le0, le1, qa[1], l[1]);
      static_assert(OFF_L0 + 2048 == OFF_VP, "halo V rows");
      const uint32_t vl0 = sb + OFF_VP - 1024 + blk0 * 2048 + (lm >> 1) * 1024 + lr * 128 + (((lm & 1) ^ lr) << 4);
      const uint32_t vl[4] = {vl0, vl0 ^ 64, vl0 ^ 32, vl0 ^ 96};
      const uint32_t obase = sb + OFF_OP + (wg == (rb2 & 1) ? 16384 : 0) + ((warp & 3) * 16 + lr) * 128 + ((lm ^ lr) << 4);
      mbar_wait(bars + 8 * BAR_STG, 0);
      {
        uint32_t km[4][4], va[8][4], vb[8][4], pp[8];
        float x[8][2];
#pragma unroll
        for (int n = 0; n < 4; n++) {
          const int blk = blk0 + 4 * (n >> 1);
          to_arr(km[n], lds128(sb + (blk == 0 ? OFF_L0 : OFF_KH + (blk - 1) * 2048) + (n & 1) * 512 + lane * 16));
        }
#pragma unroll
        for (int n = 0; n < 8; n++) {
          const uint32_t o = ((n >> 1) & 1) * 8192 + (n >> 2) * 1024;
          ldsm4t(va[n], vl[n & 1] + o);
          ldsm4t(vb[n], vl[2 + (n & 1)] + o);
        }
        const bool first = blk0 == 0 && gidx == 0;
#pragma unroll
        for (int n = 0; n < 4; n++) {
          const uint32_t(&q)[8] = qa[n >> 1][n & 1];
          float sm[4];
          mma16816_z(sm, q[0], q[1], q[2], q[3], km[n][0], km[n][1]);
          mma16816(sm, q[4], q[5], q[6], q[7], km[n][2], km[n][3]);
          if (n < 2 && first) sm[0] = sm[1] = -1e9f / 0.17677669529663687f;
          x[n][0] = le0 ? l[n >> 1][n & 1][0] : sm[0];
          x[n][1] = le1 ? l[n >> 1][n & 1][1] : sm[1];
          x[4 + n][0] = l[n >> 1][n & 1][2];
          x[4 + n][1] = l[n >> 1][n & 1][3];
        }
        quad_softmax<8>(x, pp);
#pragma unroll
        for (int n = 7; n >= 0; n--)
          attn_pv((obase ^ ((n & 1) << 6)) + ((n >> 1) & 1) * 8192 + (n >> 2) * 1024, va[n], vb[n], pp[n], maskLE);
      }
      fence_async_smem();
      nb_arrive(NB_OREADY + wg, 160);
    }

    {
      const int w = warp & 3;
      uint32_t a4[8][4];
      uint32_t d4[8];
      PROF(34 + wg);
      const uint64_t dz = mkdesc(sb + OFF_U + wg * 4096, 512, 128, 0);
      const uint64_t db2 = mkdesc(sb + OFF_T + T_B2, 128, 256, 0);
      mbar_wait(bars + 8 * BAR_T, 0);
      mbar_wait(bars + 8 * BAR_UH, 0);
      to_arr(a1[0], lds128(tb + T_A1));
      to_arr(a1[1], lds128(tb + T_A1 + 2048));
      wg_fence();
      s1(0);
      ldtw(0);
      ldtw(1);
      const uint32_t za = sb + (w < 2 ? OFF_U : OFF_H) + wg * 4096 + (w & 1) * 2048 + lane * 16;
      const uint32_t yl = (wtid ^ (4 * rank + wg)) * 16;
      const uint32_t yown = mapa(sb, rank) + yl, yrem = mapa(sb + OFF_LAND + wg * 2048, rank ^ 1) + yl;
      const uint32_t yb[2] = {mapa(bars + 8 * BAR_LAND, 0), mapa(bars + 8 * BAR_LAND, 1)};
      wg_wait<0>();
      fence_regs(d1);
      nb_sync(NB_WG + wg, 128);
      auto s4 = [&](int it) {
        wg_fence();
#pragma unroll
        for (int ks = 0; ks < 8; ks++) {
          const uint64_t d = dz + (it & 1) * 512 + (ks & 3) * 64 + (ks >> 2) * ((OFF_H - OFF_U) >> 4);
          if (ks == 0) hmma_n32<0, 1>(d4, a4[ks], d);
          else hmma_n32<1, 1>(d4, a4[ks], d);
        }
        wg_commit();
      };
      auto e4 = [&](int it) {
        fence_regs(d4);
        const uint32_t o = (yown + y_slot(wg, it)) ^ ((it >> 1) << 5), m = (yrem + it * 4096) ^ ((it >> 1) << 5);
        if (it == 0) mbar_wait(bars + 8 * BAR_LFREE, 0);
        if (it == 3) mbar_wait(bars + 8 * (BAR_DEAD + 1), 0);
        st_async128(rank ? m : o, yb[0], d4[0], d4[1], d4[2], d4[3]);
        st_async128(rank ? o : m, yb[1], d4[4], d4[5], d4[6], d4[7]);
      };
      uint32_t a2[2][2][2][4], a3[2][2][4], d2[2][2][8], d3[2][8];
      auto s2a = [&]() {
        wg_fence();
#pragma unroll
        for (int c = 0; c < 4; c++) hmma_n32<0, 0>(d2[c & 1][c >> 1], a2[0][c & 1][c >> 1], db2 + (c >> 1) * 128);
      };
      auto s2b = [&]() {
        wg_fence();
#pragma unroll
        for (int c = 0; c < 4; c++) {
          hmma_n32<1, 0>(d2[c & 1][c >> 1], a2[1][c & 1][c >> 1], db2 + (c >> 1) * 128 + 64);
          if (c & 1) wg_commit();
        }
      };
      auto done = [&](int it) {
        if (it == 0) {
          if (signaller) mbar_arrive_cluster(rbars + 8 * BAR_LFREE);
        } else if (it >= 2 && wtid == 64) {
          mbar_arrive(bars + 8 * (BAR_DEAD + it - 2));
        }
        if (w == 0) PROF3(40 + 4 * wg + it);
      };
      fft_e1<0>(d1, tw, a2[0]);
      s2a();
      fft_e1<1>(d1, tw, a2[1]);
      s2b();
      s1(1);
      ldtw(2);
      ldtw(3);
#pragma unroll
      for (int i = 0; i < 8; i++) to_arr(a4[i], lds128(tb + T_A4 + i * 2048));
#pragma unroll
      for (int it = 0; it < 4; it++) {
        if (it == 0 || it == 3) wg_wait<2>(); else wg_wait<3>();
        fence_regs(d2[0][0]);
        fence_regs(d2[1][0]);
        fft_e2<0, 0>(d2[0][0], d2[1][0], a3[0]);
        fft_e2<0, 1>(d2[0][0], d2[1][0], a3[1]);
        if (it == 0 || it == 3) wg_wait<1>(); else wg_wait<2>();
        fence_regs(d2[0][1]);
        fence_regs(d2[1][1]);
        fft_e2<1, 0>(d2[0][1], d2[1][1], a3[0]);
        fft_e2<1, 1>(d2[0][1], d2[1][1], a3[1]);
        wg_fence();
        hmma_n32<0, 0>(d3[0], a3[0][0], db2);
        hmma_n32<0, 0>(d3[1], a3[0][1], db2);
        hmma_n32<1, 0>(d3[0], a3[1][0], db2 + 64);
        hmma_n32<1, 0>(d3[1], a3[1][1], db2 + 64);
        wg_commit();
        wg_wait<1>();
        if (it > 0) e4(it - 1);
        if (it < 3) {
          fence_regs(d1);
          fft_e1<0>(d1, tw, a2[0]);
        }
        wg_wait<0>();
        fence_regs(d3[0]);
        fence_regs(d3[1]);
        if (it < 3) s2a();
        fft_e3(d3, tw, za + (it & 1) * 8192);
        if (it < 3) {
          fft_e1<1>(d1, tw, a2[1]);
          s2b();
        }
        fence_async_smem();
        nb_sync(NB_WG + wg, 128);
        done(it);
        s4(it);
        if (it < 2) s1(it + 2);
      }
      if (PEEL && MODE == 0) {
        mbar_wait(bars + 8 * BAR_FULL2, 0);
        g2_step(0, 0);
        wg_wait<1>();
      } else {
        wg_wait<0>();
      }
      if (signaller) mbar_arrive_cluster(rbars + 8 * (BAR_EMPTY2 + 4));
      e4(3);
      if (PEEL && MODE == 0) {
        wg_wait<0>();
        if (signaller) mbar_arrive_cluster(rbars + 8 * BAR_EMPTY2);
      }
      PROF(6 + wg);
    }
    }

    if (MODE != 1) {
      int s = PEEL && MODE == 0, ph = 0;
#pragma unroll 1
      for (int kb = s; kb < STAG; kb++) {
        mbar_wait(bars + 8 * (BAR_FULL2 + s), ph);
        if (kb == 1) PROF(8 + wg);
        if (warp == 4) PROF2(40 + kb);
        g2_step(s, kb);
        wg_wait<0>();
        if (kb < 16 - NS2 && signaller) mbar_arrive_cluster(rbars + 8 * (BAR_EMPTY2 + s));
        if (++s == NS2) { s = 0; ph ^= 1; }
      }
      if (STAG < 16) {
        if (wg == LAST) nb_sync(NB_LEAD, 256);
#pragma unroll
        for (int kb = STAG; kb < 16; kb++) {
          mbar_wait(bars + 8 * (BAR_FULL2 + kb % NS2), (kb / NS2) & 1);
          g2_step(kb % NS2, 1);
        }
        if (wg != LAST) nb_arrive(NB_LEAD, 256);
      }
      wg_wait<0>();
      fence_regs(acc);
      PROF(10 + wg);
      const int lr = lane & 7, lm = lane >> 3;
      const uint32_t wbase = sb + warp * 2048;
      const uint32_t base = wbase + (lr + 8 * (lm & 1)) * 128;
#pragma unroll
      for (int j = 0; j < 16; j += 2) {
        const uint32_t a = base + (j >> 3) * 16384 + ((((j & 7) + (lm >> 1)) ^ lr) << 4);
        stsm4(a, pack_bf16(acc[4 * j], acc[4 * j + 1]), pack_bf16(acc[4 * j + 2], acc[4 * j + 3]),
              pack_bf16(acc[4 * j + 4], acc[4 * j + 5]), pack_bf16(acc[4 * j + 6], acc[4 * j + 7]));
      }
      __syncwarp();
      {
        const int rr = lane >> 4, ck = lane & 7, hf = (lane >> 3) & 1;
        uint4* og = reinterpret_cast<uint4*>(p.out + (size_t)(2 * ((rb2 & 7) * 128 + warp * 16 + rr) + (rb2 >> 3)) * (2 * DM) + DM + cb2 * 128 + hf * 64 + ck * 8);
        uint4 v[8];
#pragma unroll
        for (int i = 0; i < 8; i++) v[i] = lds128(wbase + hf * 16384 + (2 * i + rr) * 128 + ((ck ^ ((2 * i + rr) & 7)) << 4));
#pragma unroll
        for (int i = 0; i < 8; i++) og[(size_t)i * 4 * (2 * DM / 8)] = v[i];
      }
      PROF(12 + wg);
    }
    cluster_sync_all();
  }
}

typedef CUresult (*EncodeFn)(CUtensorMap*, CUtensorMapDataType, cuuint32_t, void*, const cuuint64_t*, const cuuint64_t*,
                             const cuuint32_t*, const cuuint32_t*, CUtensorMapInterleave, CUtensorMapSwizzle,
                             CUtensorMapL2promotion, CUtensorMapFloatOOBfill);

void make_map(EncodeFn enc, CUtensorMap* tm, const void* base, int rank, const cuuint64_t* dims, const cuuint64_t* strides,
              const cuuint32_t* box, CUtensorMapSwizzle swz) {
  cuuint32_t es[5] = {1, 1, 1, 1, 1};
  enc(tm, CU_TENSOR_MAP_DATA_TYPE_BFLOAT16, rank, const_cast<void*>(base), dims, strides, box, es,
      CU_TENSOR_MAP_INTERLEAVE_NONE, swz, CU_TENSOR_MAP_L2_PROMOTION_L2_256B, CU_TENSOR_MAP_FLOAT_OOB_FILL_NONE);
}

}

extern "C" void kernel_launch(void* const* d_in, const int* in_sizes, int n_in, void* d_out, int out_size) {
  static EncodeFn enc = nullptr;
  static bool coresident = true;
  if (!enc) {
    void* fn = nullptr;
    cudaDriverEntryPointQueryResult qr;
    cudaGetDriverEntryPoint("cuTensorMapEncodeTiled", &fn, cudaEnableDefault, &qr);
    enc = (EncodeFn)fn;
    cudaFuncSetAttribute(fused_kernel<0>, cudaFuncAttributeMaxDynamicSharedMemorySize, SMEM_BYTES);
    cudaFuncSetAttribute(fused_kernel<1>, cudaFuncAttributeMaxDynamicSharedMemorySize, SMEM_BYTES);
    cudaFuncSetAttribute(fused_kernel<2>, cudaFuncAttributeMaxDynamicSharedMemorySize, SMEM_BYTES);
    cudaLaunchConfig_t cfg = {};
    cfg.gridDim = dim3(NCTA);
    cfg.blockDim = dim3(NTHREADS);
    cfg.dynamicSmemBytes = SMEM_BYTES;
    cudaLaunchAttribute at;
    at.id = cudaLaunchAttributeClusterDimension;
    at.val.clusterDim.x = 2;
    at.val.clusterDim.y = 1;
    at.val.clusterDim.z = 1;
    cfg.attrs = &at;
    cfg.numAttrs = 1;
    int nclusters = 0;
    if (cudaOccupancyMaxActiveClusters(&nclusters, fused_kernel<0>, &cfg) == cudaSuccess) coresident = nclusters >= NCTA / 2;
    (void)cudaGetLastError();
  }
  CUtensorMap tmX, tmW, tmWo, tmQ, tmXh, tmWh;
  {
    cuuint64_t dims[3] = {1024, 2, 1024};
    cuuint64_t str[2] = {2048, 4096};
    cuuint32_t box[3] = {64, 1, 128};
    make_map(enc, &tmX, d_in[6], 3, dims, str, box, CU_TENSOR_MAP_SWIZZLE_128B);
  }
  {
    cuuint64_t dims[3] = {1024, 1024, 3};
    cuuint64_t str[2] = {6144, 2048};
    cuuint32_t box[3] = {64, 32, 3};
    make_map(enc, &tmW, d_in[7], 3, dims, str, box, CU_TENSOR_MAP_SWIZZLE_128B);
  }
  {
    cuuint64_t dims[3] = {64, 1024, 16};
    cuuint64_t str[2] = {2048, 128};
    cuuint32_t box[3] = {64, 64, 2};
    make_map(enc, &tmWo, d_in[8], 3, dims, str, box, CU_TENSOR_MAP_SWIZZLE_128B);
  }
  {
    cuuint64_t dims[5] = {1024, 2, 2, 8, 64};
    cuuint64_t str[4] = {2048, 16 * 2048, 2 * 2048, 32 * 2048};
    cuuint32_t box[5] = {16, 2, 2, 8, 4};
    make_map(enc, &tmQ, d_in[0], 5, dims, str, box, CU_TENSOR_MAP_SWIZZLE_NONE);
  }
  {
    cuuint64_t dims[4] = {1024, 256, 2, 4};
    cuuint64_t str[3] = {4096, 2048, 256 * 4096};
    cuuint32_t box[4] = {64, 8, 2, 4};
    make_map(enc, &tmXh, d_in[6], 4, dims, str, box, CU_TENSOR_MAP_SWIZZLE_128B);
  }
  {
    cuuint64_t dims[3] = {64, 1024, 48};
    cuuint64_t str[2] = {6144, 128};
    cuuint32_t box[3] = {64, 64, 4};
    make_map(enc, &tmWh, d_in[7], 3, dims, str, box, CU_TENSOR_MAP_SWIZZLE_128B);
  }
  Params p;
  p.q = (const __nv_bfloat16*)d_in[0];
  p.k = (const __nv_bfloat16*)d_in[1];
  p.v = (const __nv_bfloat16*)d_in[2];
  p.shift_k = (const __nv_bfloat16*)d_in[3];
  p.ssm_k = (const __nv_bfloat16*)d_in[4];
  p.ssm_D = (const __nv_bfloat16*)d_in[5];
  p.x = (const __nv_bfloat16*)d_in[6];
  p.w = (const __nv_bfloat16*)d_in[7];
  p.wo = (const __nv_bfloat16*)d_in[8];
  p.out = (__nv_bfloat16*)d_out;
  if (coresident) {
    fused_kernel<0><<<NCTA, NTHREADS, SMEM_BYTES>>>(p, tmX, tmW, tmWo, tmQ, tmXh, tmWh);
  } else {
    fused_kernel<0><<<4, NTHREADS, SMEM_BYTES>>>(p, tmX, tmW, tmWo, tmQ, tmXh, tmWh);
    fused_kernel<1><<<NCTA, NTHREADS, SMEM_BYTES>>>(p, tmX, tmW, tmWo, tmQ, tmXh, tmWh);
    fused_kernel<2><<<NCTA, NTHREADS, SMEM_BYTES>>>(p, tmX, tmW, tmWo, tmQ, tmXh, tmWh);
  }
}
```

```cpp
#include <cuda_runtime.h>
#include <cuda.h>
#include <cuda_bf16.h>
#include <stdint.h>

namespace {

constexpr int SEQ = 2048;
constexpr int DM = 1024;
constexpr int NCTA = 132;
constexpr int NTHREADS = 384;

constexpr int STG1A = 32768;
constexpr int NS1A = 3;
constexpr int STG1B = 12288;
constexpr int NS1B = 5;
constexpr int OFF_1B = NS1A * STG1A;
constexpr int STG2 = 32768;
constexpr int NS2 = 5;
constexpr int STGH = 73728;
constexpr int OFF_VP = 0;
constexpr int OFF_KH = 1 * STG2;
constexpr int OFF_OP = 2 * STG2;
constexpr int OFF_Q = 3 * STG2;
constexpr int T_A4 = 0, T_TW = 16384, T_B2 = 24576, T_A1 = 28672, T_END = 32768;
constexpr int OFF_U = 163840;
constexpr int OFF_H = OFF_U + 32768;
constexpr int OFF_T = OFF_U - T_END;
constexpr int OFF_LAND = 4 * STG2;
constexpr int OFF_BAR = OFF_H + 32768;
constexpr int OFF_SC = OFF_BAR + 512;
constexpr int OFF_L0 = -2048;
constexpr int SMEM_BYTES = 2048 + OFF_BAR + 1024;
static_assert(OFF_T + T_A1 == OFF_1B + NS1B * STG1B && OFF_T + T_TW == OFF_1B + 4 * STG1B && OFF_LAND == OFF_T + T_A4, "layout");
static_assert(3 * STGH <= OFF_BAR && SMEM_BYTES <= 232448, "smem");

constexpr int BAR_FULLA = 0;
constexpr int BAR_EMPTYA = 3;
constexpr int BAR_FULLB = 6;
constexpr int BAR_EMPTYB = 11;
constexpr int BAR_FULL2 = 16;
constexpr int BAR_EMPTY2 = 21;
constexpr int BAR_T = 26;
constexpr int BAR_UH = 27;
constexpr int BAR_LFREE = 28;
constexpr int BAR_LAND = 29;
constexpr int BAR_U = 30;
constexpr int BAR_Q = 31;
constexpr int BAR_STG = 32;
constexpr int BAR_DEAD = 33;
constexpr int BAR_X = 35;
constexpr int BAR_REL = 36;

constexpr int NB_G1DONE = 1;
constexpr int NB_OREADY = 2;
constexpr int NB_WG = 4;
constexpr int NB_HELP3 = 6;
constexpr int NB_FIRST = 7;
constexpr int NB_LEAD = 8;

#define PACE 390u
#define PF0 20
#define PEEL 1
#define IDLEW 1
#define LA0 3
#define LA1 4
#define STAG 12
#define LAST 0
#define FINE 40
#define POLL1 0
#define SCHED 1
#define REG_MATH 224
#define REG_HELP 56
constexpr int SPIN_LIMIT = 1 << 20;

__device__ __align__(1024) __nv_bfloat16 g_o[SEQ * DM];
__device__ uint32_t g_flag_o[256];
__device__ uint32_t g_flag_h[4];
__device__ uint4 g_halo[128 * 128];
__device__ __align__(128) const uint32_t g_tab[T_END / 4] = {
0x3c003c00,0x3bf13bff,0,0xafd6a648,0x3c003c00,0x3b993bce,0,0xb505b303,0x3c003c00,0x3af63b50,0,0xb7e3b67c,
0x3c003c00,0x3a0f3a8a,0,0xb93ab89b,0x3bc33bfe,0x3b773bfa,0xb3c6aa48,0xb5c2acb5,0x3a6d3b3b,0x389b3a4f,0xb8c4b6d7,0xba8ab8ec,
0x381d395f,0x26483505,0xbaddb9ed,0xbbffbb99,0x30b23564,0xb848b444,0xbbeabb88,0xbac2bbb6,0x3b0e3bf6,0x3a8a3bf1,0xb78bae46,0xb89bafd6,
0x34a53913,0xa6483732,0xbba8ba2f,0xbbffbb25,0xb78bae46,0xbac2b7e3,0xbb0ebbf6,0xb848baf6,0xbba8ba2f,0xbb50bbfa,0xb4a5b913,0x367cacb5,
0x39ed3bea,0x393a3be2,0xb95fb0b2,0xba0fb179,0xb56433c6,0xb8ec2648,0xbb88bbc3,0xba4fbbff,0xbbfeba6d,0xbb25bbce,0xaa48b8c4,0x3732b303,
0xb6d7badd,0x3444b67c,0x3b3b381d,0x3bb63b50,0x38723bd9,0x37323bce,0xbaa7b23e,0xbb25b303,0xbaa7b23e,0xbbb6b67c,0xb872bbd9,0xb444bb50,
0xb872bbd9,0xacb5ba8a,0x3aa7323e,0x3bfa389b,0x3aa7323e,0x3bf139cb,0x38723bd9,0xafd63984,0x35643bc3,0x33033bb6,0xbb88b3c6,0xbbceb444,
0xbbfeb8c4,0xbb77ba0f,0x2a48ba6d,0x35c2b93a,0x36d7b81d,0x3a8aafd6,0x3b3b3add,0x389b3bf1,0x395f3bea,0x26483b25,0xb9ed30b2,0xbbffb732,
0x2e463ba8,0xa6483b99,0xbbf6b4a5,0xbbffb505,0xba2fbb0e,0xb848bbb6,0x3913b78b,0x3ac2b444,0x3bf634a5,0x3b50393a,0x2e463ba8,0xb67c3a0f,
0xb913378b,0xbbe2afd6,0xba2fbb0e,0xb179bbf1,0xb0b23b88,0xb4443b77,0xbbeab564,0xbbb6b5c2,0xb3c6bbfe,0x2cb5bbe2,0x3bc3aa48,0x3bfa3179,
0x38c43b3b,0x2fd63bff,0xba6d36d7,0xbbf12648,0xbaddb95f,0xb505bbce,0x381db9ed,0x3b99b303,0xb61f3b64,0xb7e33b50,0xbb64b61f,0xbaf6b67c,
0x361fbb64,0x393aba8a,0x3b64361f,0x3a0f389b,0xb61f3b64,0xba4f3984,0xbb64b61f,0xb8ecb9cb,0x361fbb64,0x3b25b848,0x3b64361f,0x37323ac2,
0xb8c43b3b,0xb9843b25,0xba6db6d7,0xb9cbb732,0x3addb95f,0x3bceb7e3,0x381d39ed,0x33033af6,0xbbea3564,0xbb77acb5,0xb0b2bb88,0x35c2bbfa,
0x3bc32a48,0x389b38ec,0xb3c63bfe,0xba8a3a4f,0xba2f3b0e,0xbac23af6,0xb913b78b,0xb848b7e3,0x3bf6b4a5,0x3b50acb5,0xae463ba8,0xb67c3bfa,
0xb913b78b,0xb179ba4f,0x3a2fbb0e,0x3be2b8ec,0xae463ba8,0xb9cb3b99,0xbbf634a5,0xb984b505,0xbb3b3add,0xbb993ac2,0xb6d7b81d,0xb505b848,
0x39ed30b2,0x37e335c2,0xb95f3bea,0xbaf63b77,0x3564bbc3,0x3a0fbbe2,0x3b88b3c6,0x393a3179,0xbbfe38c4,0xba4f2648,0xaa48ba6d,0x38ecbbff,
0xbbd93aa7,0xbbfa3a8a,0xb23eb872,0xacb5b89b,0x323e3872,0xafd639cb,0xbbd93aa7,0xbbf13984,0x3bd9baa7,0x3b99b848,0x323e3872,0xb5053ac2,
0xb23eb872,0x37e3bb77,0x3bd9baa7,0x3af6b5c2,0xbbfe3a6d,0xbbe23a4f,0x2a48b8c4,0x3179b8ec,0xb6d73add,0xb9843b99,0xbb3b381d,0xb9cb3505,
0x395fb0b2,0x33033444,0xb9ed3bea,0xbbce3bb6,0x3b88bbc3,0x3b77b93a,0x356433c6,0xb5c23a0f,0xbba83a2f,0xbb503a0f,0x34a5b913,0x367cb93a,
0xbb0e3bf6,0xbbe23bf1,0xb78b2e46,0xb179afd6,0xb4a53913,0xb9cb3b25,0xbba83a2f,0xb9843732,0x378bae46,0xb30337e3,0xbb0e3bf6,0xbbce3af6,
0xbadd39ed,0xba4f39cb,0x381db95f,0x38ecb984,0xbbea3b88,0xbb253ac2,0x30b2b564,0x3732b848,0xbbc33bfe,0xbbb63b77,0xb3c62a48,0x3444b5c2,
0xba6d3b3b,0xbbfa3be2,0xb8c436d7,0x2cb5b179,0xb9a839a8,0xb8ec3984,0x39a8b9a8,0x3a4fb9cb,0xb9a839a8,0xb7323848,0x39a8b9a8,0x3b25bac2,
0xb9a839a8,0xb44435c2,0x39a8b9a8,0x3bb6bb77,0xb9a839a8,0xacb53179,0x39a8b9a8,0x3bfabbe2,0xb81d395f,0xb67c393a,0x3addb9ed,0x3b50ba0f,
0xb0b23564,0x31792fd6,0x3beabb88,0x3be2bbf1,0x33c6aa48,0x3984b732,0x3bc3bbfe,0x39cbbb25,0x38c4b6d7,0x3bcebaf6,0x3a6dbb3b,0x3303b7e3,
0xb4a53913,0xb17938ec,0x3ba8ba2f,0x3be2ba4f,0x378bae46,0x39cbb505,0x3b0ebbf6,0x3984bb99,0x3ba8ba2f,0x3bcebbb6,0x34a5b913,0xb303b444,
0x3b0ebbf6,0x35c2ba0f,0xb78b2e46,0xbb77393a,0xaa4838c4,0x2cb5389b,0x3bfeba6d,0x3bfaba8a,0x3b3bb81d,0x3bf1b984,0x36d7badd,0x2fd6b9cb,
0x39edbbea,0x3505bac2,0xb95f30b2,0xbb993848,0xb564b3c6,0xbaf635c2,0xbb883bc3,0xb7e33b77,0x323e3872,0x35053848,0x3bd9baa7,0x3b99bac2,
0x3bd9baa7,0x3af6bb77,0xb23eb872,0xb7e3b5c2,0xb23eb872,0xb93ab179,0xbbd93aa7,0xba0f3be2,0xbbd93aa7,0xb8ec3bff,0x323e3872,0x3a4fa648,
0x36d7381d,0x384837e3,0x3b3bbadd,0x3ac2baf6,0x395fbbea,0x367cbbfa,0xb9edb0b2,0xbb502cb5,0xbb8833c6,0xbbe238ec,0xb5643bc3,0x31793a4f,
0x2a483a6d,0x39843505,0x3bfeb8c4,0x39cbbb99,0x3913378b,0x39cb3732,0x3a2fbb0e,0x3984bb25,0x2e46bba8,0xb303baf6,0xbbf634a5,0xbbce37e3,
0xba2f3b0e,0xb5c23bfa,0x3913378b,0x3b772cb5,0x3bf6b4a5,0x3a8aba4f,0x2e46bba8,0xb89bb8ec,0x3a6d36d7,0x3af6367c,0x38c4bb3b,0x37e3bb50,
0xb81db9ed,0xba0fb89b,0xbadd395f,0xb93a3a8a,0x30b23b88,0x38ec39cb,0x3beab564,0x3a4fb984,0x33c6bbfe,0xb732bac2,0xbbc3aa48,0xbb253848,
0x3b64361f,0x3bb635c2,0x361fbb64,0x3444bb77,0xbb64b61f,0xbbfab179,0xb61f3b64,0xacb53be2,0x3b64361f,0x3bf1a648,0x361fbb64,0xafd6bbff,
0xbb64b61f,0xbb993303,0xb61f3b64,0x35053bce,0x3bea3564,0x3bff3505,0x30b2bb88,0x2648bb99,0xbbc32a48,0xbac23444,0x33c63bfe,0x38483bb6,
0x3a6db6d7,0x367cba0f,0xb8c4bb3b,0xbb50b93a,0xb81d39ed,0x31793bf1,0x3add395f,0x3be22fd6,0x3bf634a5,0x3bce3444,0xae46bba8,0xb303bbb6,
0xb913378b,0xb5c2393a,0x3a2f3b0e,0x3b773a0f,0xae46bba8,0xb89bbbf1,0xbbf6b4a5,0xba8a2fd6,0x3a2f3b0e,0x3bff3732,0x3913b78b,0xa648bb25,
0x3b8833c6,0x3b253303,0xb564bbc3,0xb732bbce,0xaa483a6d,0x34443b50,0x3bfe38c4,0x3bb6367c,0xbb3bbadd,0xbbfab89b,0xb6d7381d,0x2cb53a8a,
0x39edb0b2,0x2fd6b984,0xb95fbbea,0xbbf1b9cb,0x3aa7323e,0x3a0f3179,0xb872bbd9,0xb93abbe2,0x38723bd9,0x3a4f3bff,0x3aa7323e,0x38eca648,
0xbaa7b23e,0xb7323303,0x38723bd9,0x3b253bce,0xb872bbd9,0xbbb6bb50,0xbaa7b23e,0xb444367c,0x395f30b2,0x389b2fd6,0xb9edbbea,0xba8abbf1,
0x3b883bc3,0x3bff3b25,0x3564b3c6,0x2648b732,0x2a4838c4,0x38483af6,0x3bfe3a6d,0x3ac237e3,0xbb3bb81d,0xb67c2cb5,0x36d73add,0x3b503bfa,
0x378b2e46,0x35c22cb5,0xbb0ebbf6,0xbb77bbfa,0x3ba83a2f,0x3a8a38ec,0xb4a5b913,0xb89bba4f,0x3b0e3bf6,0x3bff3b99,0x378b2e46,0xa648b505,
0x34a53913,0x3ac23bb6,0x3ba83a2f,0x38483444,0x33c62a48,0x2fd62648,0xbbc3bbfe,0xbbf1bbff,0x38c436d7,0x35053303,0xba6dbb3b,0xbb99bbce,
0x3add39ed,0x37e3367c,0xb81db95f,0xbaf6bb50,0x3bea3b88,0x393a389b,0xb0b2b564,0xba0fba8a,0x3c003c00,0xbbf1bbff,0,0x2fd62648,
0x3c003c00,0xbb99bbce,0,0x35053303,0x3c003c00,0xbaf6bb50,0,0x37e3367c,0x3c003c00,0xba0fba8a,0,0x393a389b,
0x3bc33bfe,0xbb77bbfa,0xb3c6aa48,0x35c22cb5,0x3a6d3b3b,0xb89bba4f,0xb8c4b6d7,0x3a8a38ec,0x381d395f,0xa648b505,0xbaddb9ed,0x3bff3b99,
0x30b23564,0x38483444,0xbbeabb88,0x3ac23bb6,0x3b0e3bf6,0xba8abbf1,0xb78bae46,0x389b2fd6,0x34a53913,0x2648b732,0xbba8ba2f,0x3bff3b25,
0xb78bae46,0x3ac237e3,0xbb0ebbf6,0x38483af6,0xbba8ba2f,0x3b503bfa,0xb4a5b913,0xb67c2cb5,0x39ed3bea,0xb93abbe2,0xb95fb0b2,0x3a0f3179,
0xb56433c6,0x38eca648,0xbb88bbc3,0x3a4f3bff,0xbbfeba6d,0x3b253bce,0xaa48b8c4,0xb7323303,0xb6d7badd,0xb444367c,0x3b3b381d,0xbbb6bb50,
0x38723bd9,0xb732bbce,0xbaa7b23e,0x3b253303,0xbaa7b23e,0x3bb6367c,0xb872bbd9,0x34443b50,0xb872bbd9,0x2cb53a8a,0x3aa7323e,0xbbfab89b,
0x3aa7323e,0xbbf1b9cb,0x38723bd9,0x2fd6b984,0x35643bc3,0xb303bbb6,0xbb88b3c6,0x3bce3444,0xbbfeb8c4,0x3b773a0f,0x2a48ba6d,0xb5c2393a,
0x36d7b81d,0xba8a2fd6,0x3b3b3add,0xb89bbbf1,0x395f3bea,0xa648bb25,0xb9ed30b2,0x3bff3732,0x2e463ba8,0x2648bb99,0xbbf6b4a5,0x3bff3505,
0xba2fbb0e,0x38483bb6,0x3913b78b,0xbac23444,0x3bf634a5,0xbb50b93a,0x2e463ba8,0x367cba0f,0xb913378b,0x3be22fd6,0xba2fbb0e,0x31793bf1,
0xb0b23b88,0x3444bb77,0xbbeab564,0x3bb635c2,0xb3c6bbfe,0xacb53be2,0x3bc3aa48,0xbbfab179,0x38c43b3b,0xafd6bbff,0xba6d36d7,0x3bf1a648,
0xbaddb95f,0x35053bce,0x381db9ed,0xbb993303,0xb61f3b64,0x37e3bb50,0xbb64b61f,0x3af6367c,0x361fbb64,0xb93a3a8a,0x3b64361f,0xba0fb89b,
0xb61f3b64,0x3a4fb984,0xbb64b61f,0x38ec39cb,0x361fbb64,0xbb253848,0x3b64361f,0xb732bac2,0xb8c43b3b,0x3984bb25,0xba6db6d7,0x39cb3732,
0x3addb95f,0xbbce37e3,0x381d39ed,0xb303baf6,0xbbea3564,0x3b772cb5,0xb0b2bb88,0xb5c23bfa,0x3bc32a48,0xb89bb8ec,0xb3c63bfe,0x3a8aba4f,
0xba2f3b0e,0x3ac2baf6,0xb913b78b,0x384837e3,0x3bf6b4a5,0xbb502cb5,0xae463ba8,0x367cbbfa,0xb913b78b,0x31793a4f,0x3a2fbb0e,0xbbe238ec,
0xae463ba8,0x39cbbb99,0xbbf634a5,0x39843505,0xbb3b3add,0x3b99bac2,0xb6d7b81d,0x35053848,0x39ed30b2,0xb7e3b5c2,0xb95f3bea,0x3af6bb77,
0x3564bbc3,0xba0f3be2,0x3b88b3c6,0xb93ab179,0xbbfe38c4,0x3a4fa648,0xaa48ba6d,0xb8ec3bff,0xbbd93aa7,0x3bfaba8a,0xb23eb872,0x2cb5389b,
0x323e3872,0x2fd6b9cb,0xbbd93aa7,0x3bf1b984,0x3bd9baa7,0xbb993848,0x323e3872,0x3505bac2,0xb23eb872,0xb7e33b77,0x3bd9baa7,0xbaf635c2,
0xbbfe3a6d,0x3be2ba4f,0x2a48b8c4,0xb17938ec,0xb6d73add,0x3984bb99,0xbb3b381d,0x39cbb505,0x395fb0b2,0xb303b444,0xb9ed3bea,0x3bcebbb6,
0x3b88bbc3,0xbb77393a,0x356433c6,0x35c2ba0f,0xbba83a2f,0x3b50ba0f,0x34a5b913,0xb67c393a,0xbb0e3bf6,0x3be2bbf1,0xb78b2e46,0x31792fd6,
0xb4a53913,0x39cbbb25,0xbba83a2f,0x3984b732,0x378bae46,0x3303b7e3,0xbb0e3bf6,0x3bcebaf6,0xbadd39ed,0x3a4fb9cb,0x381db95f,0xb8ec3984,
0xbbea3b88,0x3b25bac2,0x30b2b564,0xb7323848,0xbbc33bfe,0x3bb6bb77,0xb3c62a48,0xb44435c2,0xba6d3b3b,0x3bfabbe2,0xb8c436d7,0xacb53179,
0xb9a839a8,0x38ecb984,0x39a8b9a8,0xba4f39cb,0xb9a839a8,0x3732b848,0x39a8b9a8,0xbb253ac2,0xb9a839a8,0x3444b5c2,0x39a8b9a8,0xbbb63b77,
0xb9a839a8,0x2cb5b179,0x39a8b9a8,0xbbfa3be2,0xb81d395f,0x367cb93a,0x3addb9ed,0xbb503a0f,0xb0b23564,0xb179afd6,0x3beabb88,0xbbe23bf1,
0x33c6aa48,0xb9843732,0x3bc3bbfe,0xb9cb3b25,0x38c4b6d7,0xbbce3af6,0x3a6dbb3b,0xb30337e3,0xb4a53913,0x3179b8ec,0x3ba8ba2f,0xbbe23a4f,
0x378bae46,0xb9cb3505,0x3b0ebbf6,0xb9843b99,0x3ba8ba2f,0xbbce3bb6,0x34a5b913,0x33033444,0x3b0ebbf6,0xb5c23a0f,0xb78b2e46,0x3b77b93a,
0xaa4838c4,0xacb5b89b,0x3bfeba6d,0xbbfa3a8a,0x3b3bb81d,0xbbf13984,0x36d7badd,0xafd639cb,0x39edbbea,0xb5053ac2,0xb95f30b2,0x3b99b848,
0xb564b3c6,0x3af6b5c2,0xbb883bc3,0x37e3bb77,0x323e3872,0xb505b848,0x3bd9baa7,0xbb993ac2,0x3bd9baa7,0xbaf63b77,0xb23eb872,0x37e335c2,
0xb23eb872,0x393a3179,0xbbd93aa7,0x3a0fbbe2,0xbbd93aa7,0x38ecbbff,0x323e3872,0xba4f2648,0x36d7381d,0xb848b7e3,0x3b3bbadd,0xbac23af6,
0x395fbbea,0xb67c3bfa,0xb9edb0b2,0x3b50acb5,0xbb8833c6,0x3be2b8ec,0xb5643bc3,0xb179ba4f,0x2a483a6d,0xb984b505,0x3bfeb8c4,0xb9cb3b99,
0x3913378b,0xb9cbb732,0x3a2fbb0e,0xb9843b25,0x2e46bba8,0x33033af6,0xbbf634a5,0x3bceb7e3,0xba2f3b0e,0x35c2bbfa,0x3913378b,0xbb77acb5,
0x3bf6b4a5,0xba8a3a4f,0x2e46bba8,0x389b38ec,0x3a6d36d7,0xbaf6b67c,0x38c4bb3b,0xb7e33b50,0xb81db9ed,0x3a0f389b,0xbadd395f,0x393aba8a,
0x30b23b88,0xb8ecb9cb,0x3beab564,0xba4f3984,0x33c6bbfe,0x37323ac2,0xbbc3aa48,0x3b25b848,0x3b64361f,0xbbb6b5c2,0x361fbb64,0xb4443b77,
0xbb64b61f,0x3bfa3179,0xb61f3b64,0x2cb5bbe2,0x3b64361f,0xbbf12648,0x361fbb64,0x2fd63bff,0xbb64b61f,0x3b99b303,0xb61f3b64,0xb505bbce,
0x3bea3564,0xbbffb505,0x30b2bb88,0xa6483b99,0xbbc32a48,0x3ac2b444,0x33c63bfe,0xb848bbb6,0x3a6db6d7,0xb67c3a0f,0xb8c4bb3b,0x3b50393a,
0xb81d39ed,0xb179bbf1,0x3add395f,0xbbe2afd6,0x3bf634a5,0xbbceb444,0xae46bba8,0x33033bb6,0xb913378b,0x35c2b93a,0x3a2f3b0e,0xbb77ba0f,
0xae46bba8,0x389b3bf1,0xbbf6b4a5,0x3a8aafd6,0x3a2f3b0e,0xbbffb732,0x3913b78b,0x26483b25,0x3b8833c6,0xbb25b303,0xb564bbc3,0x37323bce,
0xaa483a6d,0xb444bb50,0x3bfe38c4,0xbbb6b67c,0xbb3bbadd,0x3bfa389b,0xb6d7381d,0xacb5ba8a,0x39edb0b2,0xafd63984,0xb95fbbea,0x3bf139cb,
0x3aa7323e,0xba0fb179,0xb872bbd9,0x393a3be2,0x38723bd9,0xba4fbbff,0x3aa7323e,0xb8ec2648,0xbaa7b23e,0x3732b303,0x38723bd9,0xbb25bbce,
0xb872bbd9,0x3bb63b50,0xbaa7b23e,0x3444b67c,0x395f30b2,0xb89bafd6,0xb9edbbea,0x3a8a3bf1,0x3b883bc3,0xbbffbb25,0x3564b3c6,0xa6483732,
0x2a4838c4,0xb848baf6,0x3bfe3a6d,0xbac2b7e3,0xbb3bb81d,0x367cacb5,0x36d73add,0xbb50bbfa,0x378b2e46,0xb5c2acb5,0xbb0ebbf6,0x3b773bfa,
0x3ba83a2f,0xba8ab8ec,0xb4a5b913,0x389b3a4f,0x3b0e3bf6,0xbbffbb99,0x378b2e46,0x26483505,0x34a53913,0xbac2bbb6,0x3ba83a2f,0xb848b444,
0x33c62a48,0xafd6a648,0xbbc3bbfe,0x3bf13bff,0x38c436d7,0xb505b303,0xba6dbb3b,0x3b993bce,0x3add39ed,0xb7e3b67c,0xb81db95f,0x3af63b50,
0x3bea3b88,0xb93ab89b,0xb0b2b564,0x3a0f3a8a,0x3c003c00,0x38ec3984,0,0xba4fb9cb,0x3c003c00,0x37323848,0,0xbb25bac2,
0x3c003c00,0x344435c2,0,0xbbb6bb77,0x3c003c00,0x2cb53179,0,0xbbfabbe2,0xb3c6aa48,0xbb50ba0f,0xbbc3bbfe,0xb67cb93a,
0xb8c4b6d7,0xbbe2bbf1,0xba6dbb3b,0x3179afd6,0xbaddb9ed,0xb9cbbb25,0xb81db95f,0x39843732,0xbbeabb88,0xb303b7e3,0xb0b2b564,0x3bce3af6,
0xbb0ebbf6,0xb179b8ec,0x378b2e46,0x3be23a4f,0xb4a5b913,0x39cb3505,0x3ba83a2f,0x39843b99,0x378b2e46,0x3bce3bb6,0x3b0e3bf6,0xb3033444,
0x3ba83a2f,0x35c23a0f,0x34a53913,0xbb77b93a,0x395f30b2,0x3bfa3a8a,0x39ed3bea,0xacb5389b,0x3b883bc3,0x2fd639cb,0xb56433c6,0xbbf1b984,
0x2a4838c4,0xbb99b848,0xbbfeba6d,0xb505bac2,0xbb3bb81d,0xb7e3bb77,0xb6d7badd,0x3af635c2,0x38723bd9,0xb5053848,0xbaa7b23e,0xbb99bac2,
0xbaa7b23e,0xbaf6bb77,0xb872bbd9,0x37e3b5c2,0xb872bbd9,0x393ab179,0x3aa7323e,0x3a0f3be2,0x3aa7323e,0x38ec3bff,0x38723bd9,0xba4fa648,
0xbb88b3c6,0xbac2baf6,0xb564bbc3,0x3848b7e3,0x2a48ba6d,0x3b502cb5,0x3bfe38c4,0x367c3bfa,0x3b3b3add,0xb1793a4f,0xb6d7381d,0xbbe2b8ec,
0xb9ed30b2,0xb9cbbb99,0xb95fbbea,0x3984b505,0xae46bba8,0x39cbb732,0x3bf634a5,0x39843b25,0x3a2f3b0e,0xb3033af6,0xb913378b,0xbbceb7e3,
0xbbf6b4a5,0xb5c2bbfa,0xae46bba8,0x3b77acb5,0x3913b78b,0x3a8a3a4f,0x3a2f3b0e,0xb89b38ec,0x3bea3564,0x37e33b50,0xb0b23b88,0xbaf6367c,
0xbbc32a48,0xb93aba8a,0xb3c6bbfe,0x3a0fb89b,0x3a6db6d7,0x3a4f3984,0x38c43b3b,0xb8ec39cb,0xb81d39ed,0xbb25b848,0xbaddb95f,0x3732bac2,
0xb61f3b64,0xbbb635c2,0xbb64b61f,0xb444bb77,0x361fbb64,0x3bfab179,0x3b64361f,0x2cb53be2,0xb61f3b64,0xbbf1a648,0xbb64b61f,0x2fd6bbff,
0x361fbb64,0x3b993303,0x3b64361f,0xb5053bce,0xba6db6d7,0xa648bb99,0x38c4bb3b,0x3bffb505,0x381d39ed,0xb8483bb6,0xbadd395f,0xbac2b444,
0xb0b2bb88,0x3b50b93a,0x3beab564,0x367c3a0f,0xb3c63bfe,0xbbe22fd6,0xbbc3aa48,0x3179bbf1,0x3a2fbb0e,0x3bceb444,0x3913378b,0xb3033bb6,
0xbbf634a5,0xb5c2b93a,0x2e46bba8,0x3b77ba0f,0x3913378b,0xb89b3bf1,0xba2f3b0e,0xba8aafd6,0x2e46bba8,0x3bffb732,0x3bf6b4a5,0xa6483b25,
0x36d7381d,0xb7323bce,0xbb3b3add,0xbb253303,0x395fbbea,0x3bb6b67c,0x39ed30b2,0xb4443b50,0xbb8833c6,0x2cb5ba8a,0x3564bbc3,0x3bfab89b,
0x2a483a6d,0xbbf139cb,0xbbfe38c4,0xafd6b984,0xbbd93aa7,0xba0f3179,0xb23eb872,0x393abbe2,0x323e3872,0xba4f3bff,0xbbd93aa7,0xb8eca648,
0x3bd9baa7,0x37323303,0x323e3872,0xbb253bce,0xb23eb872,0x3bb6bb50,0x3bd9baa7,0x3444367c,0x2a48b8c4,0x3a8abbf1,0x3bfeba6d,0x389bafd6,
0xbb3b381d,0xa648b732,0x36d7badd,0x3bffbb25,0xb9ed3bea,0xbac237e3,0xb95f30b2,0x3848baf6,0x356433c6,0xbb503bfa,0xbb883bc3,0xb67cacb5,
0x3ba8ba2f,0x35c2acb5,0xb4a53913,0xbb773bfa,0x3b0ebbf6,0x3a8ab8ec,0x378bae46,0xb89b3a4f,0x34a5b913,0x3bffbb99,0x3ba8ba2f,0xa6483505,
0xb78b2e46,0x3ac2bbb6,0x3b0ebbf6,0x3848b444,0xb81d395f,0xbbf13bff,0xbadd39ed,0xafd62648,0xb0b23564,0xbb993bce,0xbbea3b88,0xb5053303,
0x33c6aa48,0xbaf63b50,0xbbc33bfe,0xb7e3367c,0x38c4b6d7,0xba0f3a8a,0xba6d3b3b,0xb93a389b,0xb9a839a8,0x2fd6a648,0x39a8b9a8,0x3bf1bbff,
0xb9a839a8,0x3505b303,0x39a8b9a8,0x3b99bbce,0xb9a839a8,0x37e3b67c,0x39a8b9a8,0x3af6bb50,0xb9a839a8,0x393ab89b,0x39a8b9a8,0x3a0fba8a,
0x3addb9ed,0x3b77bbfa,0x381db95f,0xb5c22cb5,0x3beabb88,0x389bba4f,0x30b2b564,0xba8a38ec,0x3bc3bbfe,0x2648b505,0xb3c62a48,0xbbff3b99,
0x3a6dbb3b,0xb8483444,0xb8c436d7,0xbac23bb6,0x34a5b913,0xb89b2fd6,0xbba83a2f,0xba8a3bf1,0xb78b2e46,0xbbff3b25,0xbb0e3bf6,0x26483732,
0xbba83a2f,0xb8483af6,0xb4a53913,0x3ac2b7e3,0xbb0e3bf6,0x367c2cb5,0x378bae46,0x3b50bbfa,0xbbfe3a6d,0xb93a3be2,0xaa4838c4,0x3a0fb179,
0xb6d73add,0x38ec2648,0x3b3bb81d,0x3a4fbbff,0x395fb0b2,0x3b25bbce,0x39edbbea,0xb732b303,0x3b88bbc3,0xb444b67c,0xb564b3c6,0xbbb63b50,
0x323e3872,0x3b25b303,0x3bd9baa7,0x3732bbce,0x3bd9baa7,0x3444bb50,0xb23eb872,0xbbb6367c,0xb23eb872,0xbbfa389b,0xbbd93aa7,0xacb53a8a,
0xbbd93aa7,0x2fd63984,0x323e3872,0x3bf1b9cb,0x3b3bbadd,0x3303bbb6,0xb6d7b81d,0xbbce3444,0xb9edb0b2,0xbb773a0f,0xb95f3bea,0x35c2393a,
0xb5643bc3,0x3a8a2fd6,0x3b88b3c6,0x389bbbf1,0x3bfeb8c4,0x2648bb25,0xaa48ba6d,0xbbff3732,0xb913b78b,0xbbff3505,0xba2f3b0e,0x26483b99,
0xae463ba8,0x3ac23444,0x3bf6b4a5,0x3848bbb6,0x3a2fbb0e,0xb67cba0f,0xb913b78b,0xbb50393a,0xbbf634a5,0xb1793bf1,0xae463ba8,0x3be2afd6,
0xb8c43b3b,0x34443b77,0x3a6d36d7,0x3bb6b5c2,0x3addb95f,0xacb5bbe2,0xb81db9ed,0xbbfa3179,0xbbea3564,0xafd63bff,0x30b23b88,0x3bf12648,
0x3bc32a48,0x3505bbce,0x33c6bbfe,0xbb99b303,0x3b64361f,0x3af6b67c,0x361fbb64,0xb7e3bb50,0xbb64b61f,0xba0f389b,0xb61f3b64,0x393a3a8a,
0x3b64361f,0x38ecb9cb,0x361fbb64,0xba4fb984,0xbb64b61f,0xb7323ac2,0xb61f3b64,0x3b253848,0x30b2bb88,0xb984bb25,0xbbeab564,0xb9cb3732,
0x33c63bfe,0x3bce37e3,0x3bc3aa48,0x3303baf6,0xb8c4bb3b,0xbb772cb5,0xba6d36d7,0x35c23bfa,0x3add395f,0x389bb8ec,0x381db9ed,0xba8aba4f,
0xbbf6b4a5,0xb84837e3,0x2e463ba8,0x3ac23af6,0x3913b78b,0xb67cbbfa,0xba2fbb0e,0xbb50acb5,0x2e463ba8,0x3be238ec,0x3bf634a5,0x3179ba4f,
0xba2fbb0e,0xb9843505,0xb913378b,0x39cb3b99,0x35643bc3,0x3b993ac2,0x3b8833c6,0x3505b848,0xbbfeb8c4,0xb7e335c2,0xaa483a6d,0x3af63b77,
0x36d7b81d,0xba0fbbe2,0xbb3bbadd,0xb93a3179,0x395f3bea,0x3a4f2648,0x39edb0b2,0xb8ecbbff,0x3aa7323e,0x2cb5b89b,0xb872bbd9,0xbbfaba8a,
0x38723bd9,0x3bf13984,0x3aa7323e,0xafd6b9cb,0xbaa7b23e,0x35053ac2,0x38723bd9,0x3b993848,0xb872bbd9,0xbaf6b5c2,0xbaa7b23e,0x37e33b77,
0xb9edbbea,0xbbe2ba4f,0xb95fb0b2,0x317938ec,0x3564b3c6,0xb984bb99,0xbb88bbc3,0xb9cbb505,0x3bfe3a6d,0x3303b444,0xaa48b8c4,0xbbcebbb6,
0x36d73add,0x3b77393a,0x3b3b381d,0xb5c2ba0f,0xb78bae46,0x367c393a,0x3b0e3bf6,0x3b503a0f,0xbba8ba2f,0xb1792fd6,0x34a53913,0x3be23bf1,
0xbb0ebbf6,0xb984b732,0xb78bae46,0x39cb3b25,0xb4a5b913,0xbbcebaf6,0xbba8ba2f,0x330337e3,0x3bc33bfe,0x3a4f39cb,0x33c62a48,0xb8ecb984,
0x3a6d3b3b,0x3b253ac2,0x38c436d7,0xb732b848,0x381d395f,0x3bb63b77,0x3add39ed,0xb444b5c2,0x30b23564,0x3bfa3be2,0x3bea3b88,0xacb5b179,
0x3c003c00,0xb8ecb984,0,0x3a4f39cb,0x3c003c00,0xb732b848,0,0x3b253ac2,0x3c003c00,0xb444b5c2,0,0x3bb63b77,
0x3c003c00,0xacb5b179,0,0x3bfa3be2,0xb3c6aa48,0x3b503a0f,0xbbc3bbfe,0x367c393a,0xb8c4b6d7,0x3be23bf1,0xba6dbb3b,0xb1792fd6,
0xbaddb9ed,0x39cb3b25,0xb81db95f,0xb984b732,0xbbeabb88,0x330337e3,0xb0b2b564,0xbbcebaf6,0xbb0ebbf6,0x317938ec,0x378b2e46,0xbbe2ba4f,
0xb4a5b913,0xb9cbb505,0x3ba83a2f,0xb984bb99,0x378b2e46,0xbbcebbb6,0x3b0e3bf6,0x3303b444,0x3ba83a2f,0xb5c2ba0f,0x34a53913,0x3b77393a,
0x395f30b2,0xbbfaba8a,0x39ed3bea,0x2cb5b89b,0x3b883bc3,0xafd6b9cb,0xb56433c6,0x3bf13984,0x2a4838c4,0x3b993848,0xbbfeba6d,0x35053ac2,
0xbb3bb81d,0x37e33b77,0xb6d7badd,0xbaf6b5c2,0x38723bd9,0x3505b848,0xbaa7b23e,0x3b993ac2,0xbaa7b23e,0x3af63b77,0xb872bbd9,0xb7e335c2,
0xb872bbd9,0xb93a3179,0x3aa7323e,0xba0fbbe2,0x3aa7323e,0xb8ecbbff,0x38723bd9,0x3a4f2648,0xbb88b3c6,0x3ac23af6,0xb564bbc3,0xb84837e3,
0x2a48ba6d,0xbb50acb5,0x3bfe38c4,0xb67cbbfa,0x3b3b3add,0x3179ba4f,0xb6d7381d,0x3be238ec,0xb9ed30b2,0x39cb3b99,0xb95fbbea,0xb9843505,
0xae46bba8,0xb9cb3732,0x3bf634a5,0xb984bb25,0x3a2f3b0e,0x3303baf6,0xb913378b,0x3bce37e3,0xbbf6b4a5,0x35c23bfa,0xae46bba8,0xbb772cb5,
0x3913b78b,0xba8aba4f,0x3a2f3b0e,0x389bb8ec,0x3bea3564,0xb7e3bb50,0xb0b23b88,0x3af6b67c,0xbbc32a48,0x393a3a8a,0xb3c6bbfe,0xba0f389b,
0x3a6db6d7,0xba4fb984,0x38c43b3b,0x38ecb9cb,0xb81d39ed,0x3b253848,0xbaddb95f,0xb7323ac2,0xb61f3b64,0x3bb6b5c2,0xbb64b61f,0x34443b77,
0x361fbb64,0xbbfa3179,0x3b64361f,0xacb5bbe2,0xb61f3b64,0x3bf12648,0xbb64b61f,0xafd63bff,0x361fbb64,0xbb99b303,0x3b64361f,0x3505bbce,
0xba6db6d7,0x26483b99,0x38c4bb3b,0xbbff3505,0x381d39ed,0x3848bbb6,0xbadd395f,0x3ac23444,0xb0b2bb88,0xbb50393a,0x3beab564,0xb67cba0f,
0xb3c63bfe,0x3be2afd6,0xbbc3aa48,0xb1793bf1,0x3a2fbb0e,0xbbce3444,0x3913378b,0x3303bbb6,0xbbf634a5,0x35c2393a,0x2e46bba8,0xbb773a0f,
0x3913378b,0x389bbbf1,0xba2f3b0e,0x3a8a2fd6,0x2e46bba8,0xbbff3732,0x3bf6b4a5,0x2648bb25,0x36d7381d,0x3732bbce,0xbb3b3add,0x3b25b303,
0x395fbbea,0xbbb6367c,0x39ed30b2,0x3444bb50,0xbb8833c6,0xacb53a8a,0x3564bbc3,0xbbfa389b,0x2a483a6d,0x3bf1b9cb,0xbbfe38c4,0x2fd63984,
0xbbd93aa7,0x3a0fb179,0xb23eb872,0xb93a3be2,0x323e3872,0x3a4fbbff,0xbbd93aa7,0x38ec2648,0x3bd9baa7,0xb732b303,0x323e3872,0x3b25bbce,
0xb23eb872,0xbbb63b50,0x3bd9baa7,0xb444b67c,0x2a48b8c4,0xba8a3bf1,0x3bfeba6d,0xb89b2fd6,0xbb3b381d,0x26483732,0x36d7badd,0xbbff3b25,
0xb9ed3bea,0x3ac2b7e3,0xb95f30b2,0xb8483af6,0x356433c6,0x3b50bbfa,0xbb883bc3,0x367c2cb5,0x3ba8ba2f,0xb5c22cb5,0xb4a53913,0x3b77bbfa,
0x3b0ebbf6,0xba8a38ec,0x378bae46,0x389bba4f,0x34a5b913,0xbbff3b99,0x3ba8ba2f,0x2648b505,0xb78b2e46,0xbac23bb6,0x3b0ebbf6,0xb8483444,
0xb81d395f,0x3bf1bbff,0xbadd39ed,0x2fd6a648,0xb0b23564,0x3b99bbce,0xbbea3b88,0x3505b303,0x33c6aa48,0x3af6bb50,0xbbc33bfe,0x37e3b67c,
0x38c4b6d7,0x3a0fba8a,0xba6d3b3b,0x393ab89b,0xb9a839a8,0xafd62648,0x39a8b9a8,0xbbf13bff,0xb9a839a8,0xb5053303,0x39a8b9a8,0xbb993bce,
0xb9a839a8,0xb7e3367c,0x39a8b9a8,0xbaf63b50,0xb9a839a8,0xb93a389b,0x39a8b9a8,0xba0f3a8a,0x3addb9ed,0xbb773bfa,0x381db95f,0x35c2acb5,
0x3beabb88,0xb89b3a4f,0x30b2b564,0x3a8ab8ec,0x3bc3bbfe,0xa6483505,0xb3c62a48,0x3bffbb99,0x3a6dbb3b,0x3848b444,0xb8c436d7,0x3ac2bbb6,
0x34a5b913,0x389bafd6,0xbba83a2f,0x3a8abbf1,0xb78b2e46,0x3bffbb25,0xbb0e3bf6,0xa648b732,0xbba83a2f,0x3848baf6,0xb4a53913,0xbac237e3,
0xbb0e3bf6,0xb67cacb5,0x378bae46,0xbb503bfa,0xbbfe3a6d,0x393abbe2,0xaa4838c4,0xba0f3179,0xb6d73add,0xb8eca648,0x3b3bb81d,0xba4f3bff,
0x395fb0b2,0xbb253bce,0x39edbbea,0x37323303,0x3b88bbc3,0x3444367c,0xb564b3c6,0x3bb6bb50,0x323e3872,0xbb253303,0x3bd9baa7,0xb7323bce,
0x3bd9baa7,0xb4443b50,0xb23eb872,0x3bb6b67c,0xb23eb872,0x3bfab89b,0xbbd93aa7,0x2cb5ba8a,0xbbd93aa7,0xafd6b984,0x323e3872,0xbbf139cb,
0x3b3bbadd,0xb3033bb6,0xb6d7b81d,0x3bceb444,0xb9edb0b2,0x3b77ba0f,0xb95f3bea,0xb5c2b93a,0xb5643bc3,0xba8aafd6,0x3b88b3c6,0xb89b3bf1,
0x3bfeb8c4,0xa6483b25,0xaa48ba6d,0x3bffb732,0xb913b78b,0x3bffb505,0xba2f3b0e,0xa648bb99,0xae463ba8,0xbac2b444,0x3bf6b4a5,0xb8483bb6,
0x3a2fbb0e,0x367c3a0f,0xb913b78b,0x3b50b93a,0xbbf634a5,0x3179bbf1,0xae463ba8,0xbbe22fd6,0xb8c43b3b,0xb444bb77,0x3a6d36d7,0xbbb635c2,
0x3addb95f,0x2cb53be2,0xb81db9ed,0x3bfab179,0xbbea3564,0x2fd6bbff,0x30b23b88,0xbbf1a648,0x3bc32a48,0xb5053bce,0x33c6bbfe,0x3b993303,
0x3b64361f,0xbaf6367c,0x361fbb64,0x37e33b50,0xbb64b61f,0x3a0fb89b,0xb61f3b64,0xb93aba8a,0x3b64361f,0xb8ec39cb,0x361fbb64,0x3a4f3984,
0xbb64b61f,0x3732bac2,0xb61f3b64,0xbb25b848,0x30b2bb88,0x39843b25,0xbbeab564,0x39cbb732,0x33c63bfe,0xbbceb7e3,0x3bc3aa48,0xb3033af6,
0xb8c4bb3b,0x3b77acb5,0xba6d36d7,0xb5c2bbfa,0x3add395f,0xb89b38ec,0x381db9ed,0x3a8a3a4f,0xbbf6b4a5,0x3848b7e3,0x2e463ba8,0xbac2baf6,
0x3913b78b,0x367c3bfa,0xba2fbb0e,0x3b502cb5,0x2e463ba8,0xbbe2b8ec,0x3bf634a5,0xb1793a4f,0xba2fbb0e,0x3984b505,0xb913378b,0xb9cbbb99,
0x35643bc3,0xbb99bac2,0x3b8833c6,0xb5053848,0xbbfeb8c4,0x37e3b5c2,0xaa483a6d,0xbaf6bb77,0x36d7b81d,0x3a0f3be2,0xbb3bbadd,0x393ab179,
0x395f3bea,0xba4fa648,0x39edb0b2,0x38ec3bff,0x3aa7323e,0xacb5389b,0xb872bbd9,0x3bfa3a8a,0x38723bd9,0xbbf1b984,0x3aa7323e,0x2fd639cb,
0xbaa7b23e,0xb505bac2,0x38723bd9,0xbb99b848,0xb872bbd9,0x3af635c2,0xbaa7b23e,0xb7e3bb77,0xb9edbbea,0x3be23a4f,0xb95fb0b2,0xb179b8ec,
0x3564b3c6,0x39843b99,0xbb88bbc3,0x39cb3505,0x3bfe3a6d,0xb3033444,0xaa48b8c4,0x3bce3bb6,0x36d73add,0xbb77b93a,0x3b3b381d,0x35c23a0f,
0xb78bae46,0xb67cb93a,0x3b0e3bf6,0xbb50ba0f,0xbba8ba2f,0x3179afd6,0x34a53913,0xbbe2bbf1,0xbb0ebbf6,0x39843732,0xb78bae46,0xb9cbbb25,
0xb4a5b913,0x3bce3af6,0xbba8ba2f,0xb303b7e3,0x3bc33bfe,0xba4fb9cb,0x33c62a48,0x38ec3984,0x3a6d3b3b,0xbb25bac2,0x38c436d7,0x37323848,
0x381d395f,0xbbb6bb77,0x3add39ed,0x344435c2,0x30b23564,0xbbfabbe2,0x3bea3b88,0x2cb53179,0x3c003c00,0xafd6a648,0,0xbbf1bbff,
0x3c003c00,0xb505b303,0,0xbb99bbce,0x3c003c00,0xb7e3b67c,0,0xbaf6bb50,0x3c003c00,0xb93ab89b,0,0xba0fba8a,
0xbbc3bbfe,0x35c22cb5,0x33c62a48,0x3b773bfa,0xba6dbb3b,0x3a8a38ec,0x38c436d7,0x389b3a4f,0xb81db95f,0x3bff3b99,0x3add39ed,0x26483505,
0xb0b2b564,0x3ac23bb6,0x3bea3b88,0xb848b444,0x3b0e3bf6,0xb89bafd6,0xb78bae46,0xba8abbf1,0x34a53913,0xbbffbb25,0xbba8ba2f,0x2648b732,
0xb78bae46,0xb848baf6,0xbb0ebbf6,0x3ac237e3,0xbba8ba2f,0x367cacb5,0xb4a5b913,0x3b503bfa,0xb9edbbea,0x3a0f3179,0x395f30b2,0x393a3be2,
0x3564b3c6,0x3a4f3bff,0x3b883bc3,0xb8ec2648,0x3bfe3a6d,0xb7323303,0x2a4838c4,0xbb25bbce,0x36d73add,0xbbb6bb50,0xbb3bb81d,0x3444b67c,
0x38723bd9,0xbb25b303,0xbaa7b23e,0xb732bbce,0xbaa7b23e,0xb444bb50,0xb872bbd9,0x3bb6367c,0xb872bbd9,0x3bfa389b,0x3aa7323e,0x2cb53a8a,
0x3aa7323e,0xafd63984,0x38723bd9,0xbbf1b9cb,0xb564bbc3,0x3bce3444,0x3b8833c6,0x33033bb6,0x3bfe38c4,0xb5c2393a,0xaa483a6d,0xbb77ba0f,
0xb6d7381d,0xb89bbbf1,0xbb3bbadd,0x3a8aafd6,0xb95fbbea,0x3bff3732,0x39edb0b2,0x26483b25,0x2e463ba8,0xbbffb505,0xbbf6b4a5,0x2648bb99,
0xba2fbb0e,0x3ac2b444,0x3913b78b,0x38483bb6,0x3bf634a5,0xb67c3a0f,0x2e463ba8,0xbb50b93a,0xb913378b,0xb179bbf1,0xba2fbb0e,0x3be22fd6,
0x30b2bb88,0x3bb635c2,0x3bea3564,0xb4443b77,0x33c63bfe,0xbbfab179,0xbbc32a48,0x2cb5bbe2,0xb8c4bb3b,0x3bf1a648,0x3a6db6d7,0x2fd63bff,
0x3add395f,0xbb993303,0xb81d39ed,0xb505bbce,0xb61f3b64,0xbaf6b67c,0xbb64b61f,0x37e3bb50,0x361fbb64,0x3a0f389b,0x3b64361f,0xb93a3a8a,
0xb61f3b64,0xb8ecb9cb,0xbb64b61f,0x3a4fb984,0x361fbb64,0x37323ac2,0x3b64361f,0xbb253848,0x38c4bb3b,0x39cb3732,0x3a6d36d7,0xb9843b25,
0xbadd395f,0xb303baf6,0xb81db9ed,0x3bceb7e3,0x3beab564,0xb5c23bfa,0x30b23b88,0xbb77acb5,0xbbc3aa48,0x3a8aba4f,0x33c6bbfe,0x389b38ec,
0xba2f3b0e,0xb848b7e3,0xb913b78b,0x3ac2baf6,0x3bf6b4a5,0xb67c3bfa,0xae463ba8,0xbb502cb5,0xb913b78b,0x3be2b8ec,0x3a2fbb0e,0x31793a4f,
0xae463ba8,0xb984b505,0xbbf634a5,0x39cbbb99,0x3b3bbadd,0x35053848,0x36d7381d,0xbb993ac2,0xb9edb0b2,0x3af6bb77,0x395fbbea,0x37e335c2,
0xb5643bc3,0xb93ab179,0xbb8833c6,0x3a0fbbe2,0x3bfeb8c4,0xb8ec3bff,0x2a483a6d,0xba4f2648,0xbbd93aa7,0xacb5b89b,0xb23eb872,0x3bfaba8a,
0x323e3872,0xbbf13984,0xbbd93aa7,0x2fd6b9cb,0x3bd9baa7,0xb5053ac2,0x323e3872,0xbb993848,0xb23eb872,0x3af6b5c2,0x3bd9baa7,0xb7e33b77,
0x3bfeba6d,0xb17938ec,0xaa4838c4,0xbbe23a4f,0x36d7badd,0x39cbb505,0x3b3bb81d,0xb9843b99,0xb95f30b2,0x3bcebbb6,0x39edbbea,0x33033444,
0xbb883bc3,0x35c2ba0f,0xb564b3c6,0x3b77b93a,0xbba83a2f,0x367cb93a,0x34a5b913,0x3b50ba0f,0xbb0e3bf6,0xb179afd6,0xb78b2e46,0x3be2bbf1,
0xb4a53913,0xb9843732,0xbba83a2f,0x39cbbb25,0x378bae46,0xbbce3af6,0xbb0e3bf6,0x3303b7e3,0x3addb9ed,0xb8ec3984,0xb81d395f,0xba4f39cb,
0x3beabb88,0xb7323848,0xb0b23564,0xbb253ac2,0x3bc3bbfe,0xb44435c2,0x33c6aa48,0xbbb63b77,0x3a6dbb3b,0xacb53179,0x38c4b6d7,0xbbfa3be2,
0xb9a839a8,0x3a4fb9cb,0x39a8b9a8,0x38ecb984,0xb9a839a8,0x3b25bac2,0x39a8b9a8,0x3732b848,0xb9a839a8,0x3bb6bb77,0x39a8b9a8,0x3444b5c2,
0xb9a839a8,0x3bfabbe2,0x39a8b9a8,0x2cb5b179,0x381db95f,0xbb503a0f,0xbadd39ed,0xb67c393a,0x30b2b564,0xbbe23bf1,0xbbea3b88,0x31792fd6,
0xb3c62a48,0xb9cb3b25,0xbbc33bfe,0x3984b732,0xb8c436d7,0xb30337e3,0xba6d3b3b,0x3bcebaf6,0xb4a53913,0x3be2ba4f,0x3ba8ba2f,0x3179b8ec,
0x378bae46,0x3984bb99,0x3b0ebbf6,0xb9cb3505,0x3ba8ba2f,0xb303b444,0x34a5b913,0xbbce3bb6,0x3b0ebbf6,0xbb77393a,0xb78b2e46,0xb5c23a0f,
0x2a48b8c4,0xbbfa3a8a,0xbbfe3a6d,0x2cb5389b,0xbb3b381d,0xafd639cb,0xb6d73add,0x3bf1b984,0xb9ed3bea,0x3b99b848,0x395fb0b2,0x3505bac2,
0x356433c6,0x37e3bb77,0x3b88bbc3,0xbaf635c2,0x323e3872,0x3b99bac2,0x3bd9baa7,0xb505b848,0x3bd9baa7,0xb7e3b5c2,0xb23eb872,0xbaf63b77,
0xb23eb872,0xba0f3be2,0xbbd93aa7,0x393a3179,0xbbd93aa7,0x3a4fa648,0x323e3872,0x38ecbbff,0xb6d7b81d,0xbac23af6,0xbb3b3add,0x384837e3,
0xb95f3bea,0x3b50acb5,0x39ed30b2,0x367cbbfa,0x3b88b3c6,0xb179ba4f,0x3564bbc3,0xbbe238ec,0xaa48ba6d,0xb9cb3b99,0xbbfe38c4,0x39843505,
0x3913378b,0x3984bb25,0x3a2fbb0e,0xb9cbb732,0x2e46bba8,0xbbce37e3,0xbbf634a5,0x33033af6,0xba2f3b0e,0x3b772cb5,0x3913378b,0x35c2bbfa,
0x3bf6b4a5,0xb89bb8ec,0x2e46bba8,0xba8a3a4f,0xba6db6d7,0xb7e33b50,0xb8c43b3b,0x3af6367c,0x381d39ed,0x393aba8a,0x3addb95f,0xba0fb89b,
0xb0b2bb88,0xba4f3984,0xbbea3564,0x38ec39cb,0xb3c63bfe,0x3b25b848,0x3bc32a48,0xb732bac2,0x3b64361f,0x3444bb77,0x361fbb64,0xbbb6b5c2,
0xbb64b61f,0xacb53be2,0xb61f3b64,0x3bfa3179,0x3b64361f,0xafd6bbff,0x361fbb64,0xbbf12648,0xbb64b61f,0x35053bce,0xb61f3b64,0x3b99b303,
0xbbeab564,0xa6483b99,0xb0b23b88,0x3bff3505,0x3bc3aa48,0xb848bbb6,0xb3c6bbfe,0xbac23444,0xba6d36d7,0x3b50393a,0x38c43b3b,0x367cba0f,
0x381db9ed,0xbbe2afd6,0xbaddb95f,0x31793bf1,0x3bf634a5,0xb303bbb6,0xae46bba8,0xbbceb444,0xb913378b,0x3b773a0f,0x3a2f3b0e,0x35c2b93a,
0xae46bba8,0xba8a2fd6,0xbbf6b4a5,0x389b3bf1,0x3a2f3b0e,0xa648bb25,0x3913b78b,0xbbffb732,0xbb88b3c6,0x37323bce,0x35643bc3,0x3b253303,
0x2a48ba6d,0xbbb6b67c,0xbbfeb8c4,0x34443b50,0x3b3b3add,0xacb5ba8a,0x36d7b81d,0xbbfab89b,0xb9ed30b2,0x3bf139cb,0x395f3bea,0x2fd6b984,
0x3aa7323e,0xb93abbe2,0xb872bbd9,0xba0fb179,0x38723bd9,0x38eca648,0x3aa7323e,0xba4fbbff,0xbaa7b23e,0x3b253bce,0x38723bd9,0x3732b303,
0xb872bbd9,0xb444367c,0xbaa7b23e,0x3bb63b50,0xb95fb0b2,0x3a8a3bf1,0x39ed3bea,0x389b2fd6,0xbb88bbc3,0xa6483732,0xb56433c6,0x3bff3b25,
0xaa48b8c4,0xbac2b7e3,0xbbfeba6d,0x38483af6,0x3b3b381d,0xbb50bbfa,0xb6d7badd,0xb67c2cb5,0x378b2e46,0xbb77bbfa,0xbb0ebbf6,0xb5c2acb5,
0x3ba83a2f,0xb89bba4f,0xb4a5b913,0xba8ab8ec,0x3b0e3bf6,0xa648b505,0x378b2e46,0xbbffbb99,0x34a53913,0x38483444,0x3ba83a2f,0xbac2bbb6,
0xb3c6aa48,0x3bf13bff,0x3bc33bfe,0x2fd62648,0xb8c4b6d7,0x3b993bce,0x3a6d3b3b,0x35053303,0xbaddb9ed,0x3af63b50,0x381d395f,0x37e3367c,
0xbbeabb88,0x3a0f3a8a,0x30b23564,0x393a389b,0x3c003c00,0x2fd62648,0,0x3bf13bff,0x3c003c00,0x35053303,0,0x3b993bce,
0x3c003c00,0x37e3367c,0,0x3af63b50,0x3c003c00,0x393a389b,0,0x3a0f3a8a,0xbbc3bbfe,0xb5c2acb5,0x33c62a48,0xbb77bbfa,
0xba6dbb3b,0xba8ab8ec,0x38c436d7,0xb89bba4f,0xb81db95f,0xbbffbb99,0x3add39ed,0xa648b505,0xb0b2b564,0xbac2bbb6,0x3bea3b88,0x38483444,
0x3b0e3bf6,0x389b2fd6,0xb78bae46,0x3a8a3bf1,0x34a53913,0x3bff3b25,0xbba8ba2f,0xa6483732,0xb78bae46,0x38483af6,0xbb0ebbf6,0xbac2b7e3,
0xbba8ba2f,0xb67c2cb5,0xb4a5b913,0xbb50bbfa,0xb9edbbea,0xba0fb179,0x395f30b2,0xb93abbe2,0x3564b3c6,0xba4fbbff,0x3b883bc3,0x38eca648,
0x3bfe3a6d,0x3732b303,0x2a4838c4,0x3b253bce,0x36d73add,0x3bb63b50,0xbb3bb81d,0xb444367c,0x38723bd9,0x3b253303,0xbaa7b23e,0x37323bce,
0xbaa7b23e,0x34443b50,0xb872bbd9,0xbbb6b67c,0xb872bbd9,0xbbfab89b,0x3aa7323e,0xacb5ba8a,0x3aa7323e,0x2fd6b984,0x38723bd9,0x3bf139cb,
0xb564bbc3,0xbbceb444,0x3b8833c6,0xb303bbb6,0x3bfe38c4,0x35c2b93a,0xaa483a6d,0x3b773a0f,0xb6d7381d,0x389b3bf1,0xbb3bbadd,0xba8a2fd6,
0xb95fbbea,0xbbffb732,0x39edb0b2,0xa648bb25,0x2e463ba8,0x3bff3505,0xbbf6b4a5,0xa6483b99,0xba2fbb0e,0xbac23444,0x3913b78b,0xb848bbb6,
0x3bf634a5,0x367cba0f,0x2e463ba8,0x3b50393a,0xb913378b,0x31793bf1,0xba2fbb0e,0xbbe2afd6,0x30b2bb88,0xbbb6b5c2,0x3bea3564,0x3444bb77,
0x33c63bfe,0x3bfa3179,0xbbc32a48,0xacb53be2,0xb8c4bb3b,0xbbf12648,0x3a6db6d7,0xafd6bbff,0x3add395f,0x3b99b303,0xb81d39ed,0x35053bce,
0xb61f3b64,0x3af6367c,0xbb64b61f,0xb7e33b50,0x361fbb64,0xba0fb89b,0x3b64361f,0x393aba8a,0xb61f3b64,0x38ec39cb,0xbb64b61f,0xba4f3984,
0x361fbb64,0xb732bac2,0x3b64361f,0x3b25b848,0x38c4bb3b,0xb9cbb732,0x3a6d36d7,0x3984bb25,0xbadd395f,0x33033af6,0xb81db9ed,0xbbce37e3,
0x3beab564,0x35c2bbfa,0x30b23b88,0x3b772cb5,0xbbc3aa48,0xba8a3a4f,0x33c6bbfe,0xb89bb8ec,0xba2f3b0e,0x384837e3,0xb913b78b,0xbac23af6,
0x3bf6b4a5,0x367cbbfa,0xae463ba8,0x3b50acb5,0xb913b78b,0xbbe238ec,0x3a2fbb0e,0xb179ba4f,0xae463ba8,0x39843505,0xbbf634a5,0xb9cb3b99,
0x3b3bbadd,0xb505b848,0x36d7381d,0x3b99bac2,0xb9edb0b2,0xbaf63b77,0x395fbbea,0xb7e3b5c2,0xb5643bc3,0x393a3179,0xbb8833c6,0xba0f3be2,
0x3bfeb8c4,0x38ecbbff,0x2a483a6d,0x3a4fa648,0xbbd93aa7,0x2cb5389b,0xb23eb872,0xbbfa3a8a,0x323e3872,0x3bf1b984,0xbbd93aa7,0xafd639cb,
0x3bd9baa7,0x3505bac2,0x323e3872,0x3b99b848,0xb23eb872,0xbaf635c2,0x3bd9baa7,0x37e3bb77,0x3bfeba6d,0x3179b8ec,0xaa4838c4,0x3be2ba4f,
0x36d7badd,0xb9cb3505,0x3b3bb81d,0x3984bb99,0xb95f30b2,0xbbce3bb6,0x39edbbea,0xb303b444,0xbb883bc3,0xb5c23a0f,0xb564b3c6,0xbb77393a,
0xbba83a2f,0xb67c393a,0x34a5b913,0xbb503a0f,0xbb0e3bf6,0x31792fd6,0xb78b2e46,0xbbe23bf1,0xb4a53913,0x3984b732,0xbba83a2f,0xb9cb3b25,
0x378bae46,0x3bcebaf6,0xbb0e3bf6,0xb30337e3,0x3addb9ed,0x38ecb984,0xb81d395f,0x3a4fb9cb,0x3beabb88,0x3732b848,0xb0b23564,0x3b25bac2,
0x3bc3bbfe,0x3444b5c2,0x33c6aa48,0x3bb6bb77,0x3a6dbb3b,0x2cb5b179,0x38c4b6d7,0x3bfabbe2,0xb9a839a8,0xba4f39cb,0x39a8b9a8,0xb8ec3984,
0xb9a839a8,0xbb253ac2,0x39a8b9a8,0xb7323848,0xb9a839a8,0xbbb63b77,0x39a8b9a8,0xb44435c2,0xb9a839a8,0xbbfa3be2,0x39a8b9a8,0xacb53179,
0x381db95f,0x3b50ba0f,0xbadd39ed,0x367cb93a,0x30b2b564,0x3be2bbf1,0xbbea3b88,0xb179afd6,0xb3c62a48,0x39cbbb25,0xbbc33bfe,0xb9843732,
0xb8c436d7,0x3303b7e3,0xba6d3b3b,0xbbce3af6,0xb4a53913,0xbbe23a4f,0x3ba8ba2f,0xb17938ec,0x378bae46,0xb9843b99,0x3b0ebbf6,0x39cbb505,
0x3ba8ba2f,0x33033444,0x34a5b913,0x3bcebbb6,0x3b0ebbf6,0x3b77b93a,0xb78b2e46,0x35c2ba0f,0x2a48b8c4,0x3bfaba8a,0xbbfe3a6d,0xacb5b89b,
0xbb3b381d,0x2fd6b9cb,0xb6d73add,0xbbf13984,0xb9ed3bea,0xbb993848,0x395fb0b2,0xb5053ac2,0x356433c6,0xb7e33b77,0x3b88bbc3,0x3af6b5c2,
0x323e3872,0xbb993ac2,0x3bd9baa7,0x35053848,0x3bd9baa7,0x37e335c2,0xb23eb872,0x3af6bb77,0xb23eb872,0x3a0fbbe2,0xbbd93aa7,0xb93ab179,
0xbbd93aa7,0xba4f2648,0x323e3872,0xb8ec3bff,0xb6d7b81d,0x3ac2baf6,0xbb3b3add,0xb848b7e3,0xb95f3bea,0xbb502cb5,0x39ed30b2,0xb67c3bfa,
0x3b88b3c6,0x31793a4f,0x3564bbc3,0x3be2b8ec,0xaa48ba6d,0x39cbbb99,0xbbfe38c4,0xb984b505,0x3913378b,0xb9843b25,0x3a2fbb0e,0x39cb3732,
0x2e46bba8,0x3bceb7e3,0xbbf634a5,0xb303baf6,0xba2f3b0e,0xbb77acb5,0x3913378b,0xb5c23bfa,0x3bf6b4a5,0x389b38ec,0x2e46bba8,0x3a8aba4f,
0xba6db6d7,0x37e3bb50,0xb8c43b3b,0xbaf6b67c,0x381d39ed,0xb93a3a8a,0x3addb95f,0x3a0f389b,0xb0b2bb88,0x3a4fb984,0xbbea3564,0xb8ecb9cb,
0xb3c63bfe,0xbb253848,0x3bc32a48,0x37323ac2,0x3b64361f,0xb4443b77,0x361fbb64,0x3bb635c2,0xbb64b61f,0x2cb5bbe2,0xb61f3b64,0xbbfab179,
0x3b64361f,0x2fd63bff,0x361fbb64,0x3bf1a648,0xbb64b61f,0xb505bbce,0xb61f3b64,0xbb993303,0xbbeab564,0x2648bb99,0xb0b23b88,0xbbffb505,
0x3bc3aa48,0x38483bb6,0xb3c6bbfe,0x3ac2b444,0xba6d36d7,0xbb50b93a,0x38c43b3b,0xb67c3a0f,0x381db9ed,0x3be22fd6,0xbaddb95f,0xb179bbf1,
0x3bf634a5,0x33033bb6,0xae46bba8,0x3bce3444,0xb913378b,0xbb77ba0f,0x3a2f3b0e,0xb5c2393a,0xae46bba8,0x3a8aafd6,0xbbf6b4a5,0xb89bbbf1,
0x3a2f3b0e,0x26483b25,0x3913b78b,0x3bff3732,0xbb88b3c6,0xb732bbce,0x35643bc3,0xbb25b303,0x2a48ba6d,0x3bb6367c,0xbbfeb8c4,0xb444bb50,
0x3b3b3add,0x2cb53a8a,0x36d7b81d,0x3bfa389b,0xb9ed30b2,0xbbf1b9cb,0x395f3bea,0xafd63984,0x3aa7323e,0x393a3be2,0xb872bbd9,0x3a0f3179,
0x38723bd9,0xb8ec2648,0x3aa7323e,0x3a4f3bff,0xbaa7b23e,0xbb25bbce,0x38723bd9,0xb7323303,0xb872bbd9,0x3444b67c,0xbaa7b23e,0xbbb6bb50,
0xb95fb0b2,0xba8abbf1,0x39ed3bea,0xb89bafd6,0xbb88bbc3,0x2648b732,0xb56433c6,0xbbffbb25,0xaa48b8c4,0x3ac237e3,0xbbfeba6d,0xb848baf6,
0x3b3b381d,0x3b503bfa,0xb6d7badd,0x367cacb5,0x378b2e46,0x3b773bfa,0xbb0ebbf6,0x35c22cb5,0x3ba83a2f,0x389b3a4f,0xb4a5b913,0x3a8a38ec,
0x3b0e3bf6,0x26483505,0x378b2e46,0x3bff3b99,0x34a53913,0xb848b444,0x3ba83a2f,0x3ac23bb6,0xb3c6aa48,0xbbf1bbff,0x3bc33bfe,0xafd6a648,
0xb8c4b6d7,0xbb99bbce,0x3a6d3b3b,0xb505b303,0xbaddb9ed,0xbaf6bb50,0x381d395f,0xb7e3b67c,0xbbeabb88,0xba0fba8a,0x30b23564,0xb93ab89b,
0x3c003c00,0xba4fb9cb,0,0xb8ecb984,0x3c003c00,0xbb25bac2,0,0xb732b848,0x3c003c00,0xbbb6bb77,0,0xb444b5c2,
0x3c003c00,0xbbfabbe2,0,0xacb5b179,0x33c62a48,0x367c393a,0x3bc33bfe,0xbb50ba0f,0x38c436d7,0xb1792fd6,0x3a6d3b3b,0xbbe2bbf1,
0x3add39ed,0xb984b732,0x381d395f,0xb9cbbb25,0x3bea3b88,0xbbcebaf6,0x30b23564,0xb303b7e3,0xbb0ebbf6,0x3be23a4f,0x378b2e46,0x317938ec,
0xb4a5b913,0x39843b99,0x3ba83a2f,0xb9cbb505,0x378b2e46,0xb3033444,0x3b0e3bf6,0xbbcebbb6,0x3ba83a2f,0xbb77b93a,0x34a53913,0xb5c2ba0f,
0xb95fb0b2,0x2cb5b89b,0xb9edbbea,0x3bfa3a8a,0xbb88bbc3,0x3bf13984,0x3564b3c6,0x2fd639cb,0xaa48b8c4,0x35053ac2,0x3bfe3a6d,0xbb99b848,
0x3b3b381d,0xbaf6b5c2,0x36d73add,0xb7e3bb77,0x38723bd9,0xbb99bac2,0xbaa7b23e,0x3505b848,0xbaa7b23e,0x37e3b5c2,0xb872bbd9,0x3af63b77,
0xb872bbd9,0x3a0f3be2,0x3aa7323e,0xb93a3179,0x3aa7323e,0xba4fa648,0x38723bd9,0xb8ecbbff,0x3b8833c6,0xb84837e3,0x35643bc3,0xbac2baf6,
0xaa483a6d,0xb67cbbfa,0xbbfeb8c4,0x3b502cb5,0xbb3bbadd,0x3be238ec,0x36d7b81d,0xb1793a4f,0x39edb0b2,0xb9843505,0x395f3bea,0xb9cbbb99,
0xae46bba8,0x39843b25,0x3bf634a5,0xb9cb3732,0x3a2f3b0e,0xbbceb7e3,0xb913378b,0x3303baf6,0xbbf6b4a5,0x3b77acb5,0xae46bba8,0x35c23bfa,
0x3913b78b,0xb89b38ec,0x3a2f3b0e,0xba8aba4f,0xbbeab564,0x3af6b67c,0x30b2bb88,0x37e33b50,0x3bc3aa48,0xba0f389b,0x33c63bfe,0xb93aba8a,
0xba6d36d7,0x38ecb9cb,0xb8c4bb3b,0x3a4f3984,0x381db9ed,0xb7323ac2,0x3add395f,0xbb25b848,0xb61f3b64,0xb444bb77,0xbb64b61f,0x3bb6b5c2,
0x361fbb64,0x2cb53be2,0x3b64361f,0xbbfa3179,0xb61f3b64,0x2fd6bbff,0xbb64b61f,0x3bf12648,0x361fbb64,0xb5053bce,0x3b64361f,0xbb99b303,
0x3a6d36d7,0xbbff3505,0xb8c43b3b,0xa648bb99,0xb81db9ed,0x3ac23444,0x3addb95f,0xb8483bb6,0x30b23b88,0xb67cba0f,0xbbea3564,0x3b50b93a,
0x33c6bbfe,0xb1793bf1,0x3bc32a48,0xbbe22fd6,0x3a2fbb0e,0xb3033bb6,0x3913378b,0xbbce3444,0xbbf634a5,0x3b77ba0f,0x2e46bba8,0x35c2393a,
0x3913378b,0xba8aafd6,0xba2f3b0e,0x389bbbf1,0x2e46bba8,0xa6483b25,0x3bf6b4a5,0xbbff3732,0xb6d7b81d,0x3b25b303,0x3b3bbadd,0xb7323bce,
0xb95f3bea,0x3444bb50,0xb9edb0b2,0x3bb6b67c,0x3b88b3c6,0xbbfa389b,0xb5643bc3,0x2cb5ba8a,0xaa48ba6d,0x2fd63984,0x3bfeb8c4,0xbbf139cb,
0xbbd93aa7,0x393abbe2,0xb23eb872,0x3a0fb179,0x323e3872,0xb8eca648,0xbbd93aa7,0x3a4fbbff,0x3bd9baa7,0xbb253bce,0x323e3872,0xb732b303,
0xb23eb872,0x3444367c,0x3bd9baa7,0xbbb63b50,0xaa4838c4,0xb89b2fd6,0xbbfe3a6d,0x3a8abbf1,0x3b3bb81d,0xbbff3b25,0xb6d73add,0xa648b732,
0x39edbbea,0xb8483af6,0x395fb0b2,0xbac237e3,0xb564b3c6,0x367c2cb5,0x3b88bbc3,0xbb503bfa,0x3ba8ba2f,0xbb773bfa,0xb4a53913,0xb5c22cb5,
0x3b0ebbf6,0xb89b3a4f,0x378bae46,0xba8a38ec,0x34a5b913,0xa6483505,0x3ba8ba2f,0xbbff3b99,0xb78b2e46,0x3848b444,0x3b0ebbf6,0xbac23bb6,
0x381db95f,0x2fd6a648,0x3addb9ed,0xbbf13bff,0x30b2b564,0x3505b303,0x3beabb88,0xbb993bce,0xb3c62a48,0x37e3b67c,0x3bc3bbfe,0xbaf63b50,
0xb8c436d7,0x393ab89b,0x3a6dbb3b,0xba0f3a8a,0xb9a839a8,0x3bf1bbff,0x39a8b9a8,0xafd62648,0xb9a839a8,0x3b99bbce,0x39a8b9a8,0xb5053303,
0xb9a839a8,0x3af6bb50,0x39a8b9a8,0xb7e3367c,0xb9a839a8,0x3a0fba8a,0x39a8b9a8,0xb93a389b,0xbadd39ed,0x35c2acb5,0xb81d395f,0x3b77bbfa,
0xbbea3b88,0x3a8ab8ec,0xb0b23564,0x389bba4f,0xbbc33bfe,0x3bffbb99,0x33c6aa48,0x2648b505,0xba6d3b3b,0x3ac2bbb6,0x38c4b6d7,0xb8483444,
0x34a5b913,0xba8a3bf1,0xbba83a2f,0x389bafd6,0xb78b2e46,0x26483732,0xbb0e3bf6,0x3bffbb25,0xbba83a2f,0x3ac2b7e3,0xb4a53913,0x3848baf6,
0xbb0e3bf6,0x3b50bbfa,0x378bae46,0xb67cacb5,0x3bfeba6d,0xba0f3179,0x2a48b8c4,0xb93a3be2,0x36d7badd,0xba4f3bff,0xbb3b381d,0x38ec2648,
0xb95f30b2,0x37323303,0xb9ed3bea,0x3b25bbce,0xbb883bc3,0x3bb6bb50,0x356433c6,0xb444b67c,0x323e3872,0x3732bbce,0x3bd9baa7,0xbb253303,
0x3bd9baa7,0xbbb6367c,0xb23eb872,0xb4443b50,0xb23eb872,0xacb53a8a,0xbbd93aa7,0x3bfab89b,0xbbd93aa7,0x3bf1b9cb,0x323e3872,0xafd6b984,
0xbb3b3add,0x3bceb444,0x36d7381d,0x3303bbb6,0x39ed30b2,0xb5c2b93a,0x395fbbea,0xbb773a0f,0x3564bbc3,0xb89b3bf1,0xbb8833c6,0x3a8a2fd6,
0xbbfe38c4,0x3bffb732,0x2a483a6d,0x2648bb25,0xb913b78b,0x26483b99,0xba2f3b0e,0x3bffb505,0xae463ba8,0x3848bbb6,0x3bf6b4a5,0xbac2b444,
0x3a2fbb0e,0xbb50393a,0xb913b78b,0x367c3a0f,0xbbf634a5,0x3be2afd6,0xae463ba8,0x3179bbf1,0x38c4bb3b,0xbbb635c2,0xba6db6d7,0x34443b77,
0xbadd395f,0x3bfab179,0x381d39ed,0xacb5bbe2,0x3beab564,0xbbf1a648,0xb0b2bb88,0xafd63bff,0xbbc3aa48,0x3b993303,0xb3c63bfe,0x3505bbce,
0x3b64361f,0xb7e3bb50,0x361fbb64,0xbaf6367c,0xbb64b61f,0x393a3a8a,0xb61f3b64,0x3a0fb89b,0x3b64361f,0xba4fb984,0x361fbb64,0xb8ec39cb,
0xbb64b61f,0x3b253848,0xb61f3b64,0x3732bac2,0xb0b23b88,0x39cbb732,0x3bea3564,0xb984bb25,0xb3c6bbfe,0xb3033af6,0xbbc32a48,0x3bce37e3,
0x38c43b3b,0xb5c2bbfa,0x3a6db6d7,0xbb772cb5,0xbaddb95f,0x3a8a3a4f,0xb81d39ed,0x389bb8ec,0xbbf6b4a5,0x3ac23af6,0x2e463ba8,0x3848b7e3,
0x3913b78b,0xbb50acb5,0xba2fbb0e,0x367c3bfa,0x2e463ba8,0x3179ba4f,0x3bf634a5,0xbbe2b8ec,0xba2fbb0e,0x39cb3b99,0xb913378b,0x3984b505,
0xb564bbc3,0xb5053848,0xbb88b3c6,0x3b993ac2,0x3bfe38c4,0xbaf6bb77,0x2a48ba6d,0xb7e335c2,0xb6d7381d,0x393ab179,0x3b3b3add,0xba0fbbe2,
0xb95fbbea,0x38ec3bff,0xb9ed30b2,0x3a4f2648,0x3aa7323e,0xbbfaba8a,0xb872bbd9,0xacb5389b,0x38723bd9,0xafd6b9cb,0x3aa7323e,0xbbf1b984,
0xbaa7b23e,0x3b993848,0x38723bd9,0xb505bac2,0xb872bbd9,0x37e33b77,0xbaa7b23e,0x3af635c2,0x39ed3bea,0xb179b8ec,0x395f30b2,0xbbe2ba4f,
0xb56433c6,0x39cb3505,0x3b883bc3,0xb984bb99,0xbbfeba6d,0x3bce3bb6,0x2a4838c4,0x3303b444,0xb6d7badd,0x35c23a0f,0xbb3bb81d,0x3b77393a,
0xb78bae46,0x3b503a0f,0x3b0e3bf6,0xb67cb93a,0xbba8ba2f,0x3be23bf1,0x34a53913,0x3179afd6,0xbb0ebbf6,0x39cb3b25,0xb78bae46,0x39843732,
0xb4a5b913,0x330337e3,0xbba8ba2f,0x3bce3af6,0xbbc3bbfe,0x38ec3984,0xb3c6aa48,0x3a4f39cb,0xba6dbb3b,0x37323848,0xb8c4b6d7,0x3b253ac2,
0xb81db95f,0x344435c2,0xbaddb9ed,0x3bb63b77,0xb0b2b564,0x2cb53179,0xbbeabb88,0x3bfa3be2,0x3c003c00,0x3a4f39cb,0,0x38ec3984,
0x3c003c00,0x3b253ac2,0,0x37323848,0x3c003c00,0x3bb63b77,0,0x344435c2,0x3c003c00,0x3bfa3be2,0,0x2cb53179,
0x33c62a48,0xb67cb93a,0x3bc33bfe,0x3b503a0f,0x38c436d7,0x3179afd6,0x3a6d3b3b,0x3be23bf1,0x3add39ed,0x39843732,0x381d395f,0x39cb3b25,
0x3bea3b88,0x3bce3af6,0x30b23564,0x330337e3,0xbb0ebbf6,0xbbe2ba4f,0x378b2e46,0xb179b8ec,0xb4a5b913,0xb984bb99,0x3ba83a2f,0x39cb3505,
0x378b2e46,0x3303b444,0x3b0e3bf6,0x3bce3bb6,0x3ba83a2f,0x3b77393a,0x34a53913,0x35c23a0f,0xb95fb0b2,0xacb5389b,0xb9edbbea,0xbbfaba8a,
0xbb88bbc3,0xbbf1b984,0x3564b3c6,0xafd6b9cb,0xaa48b8c4,0xb505bac2,0x3bfe3a6d,0x3b993848,0x3b3b381d,0x3af635c2,0x36d73add,0x37e33b77,
0x38723bd9,0x3b993ac2,0xbaa7b23e,0xb5053848,0xbaa7b23e,0xb7e335c2,0xb872bbd9,0xbaf6bb77,0xb872bbd9,0xba0fbbe2,0x3aa7323e,0x393ab179,
0x3aa7323e,0x3a4f2648,0x38723bd9,0x38ec3bff,0x3b8833c6,0x3848b7e3,0x35643bc3,0x3ac23af6,0xaa483a6d,0x367c3bfa,0xbbfeb8c4,0xbb50acb5,
0xbb3bbadd,0xbbe2b8ec,0x36d7b81d,0x3179ba4f,0x39edb0b2,0x3984b505,0x395f3bea,0x39cb3b99,0xae46bba8,0xb984bb25,0x3bf634a5,0x39cbb732,
0x3a2f3b0e,0x3bce37e3,0xb913378b,0xb3033af6,0xbbf6b4a5,0xbb772cb5,0xae46bba8,0xb5c2bbfa,0x3913b78b,0x389bb8ec,0x3a2f3b0e,0x3a8a3a4f,
0xbbeab564,0xbaf6367c,0x30b2bb88,0xb7e3bb50,0x3bc3aa48,0x3a0fb89b,0x33c63bfe,0x393a3a8a,0xba6d36d7,0xb8ec39cb,0xb8c4bb3b,0xba4fb984,
0x381db9ed,0x3732bac2,0x3add395f,0x3b253848,0xb61f3b64,0x34443b77,0xbb64b61f,0xbbb635c2,0x361fbb64,0xacb5bbe2,0x3b64361f,0x3bfab179,
0xb61f3b64,0xafd63bff,0xbb64b61f,0xbbf1a648,0x361fbb64,0x3505bbce,0x3b64361f,0x3b993303,0x3a6d36d7,0x3bffb505,0xb8c43b3b,0x26483b99,
0xb81db9ed,0xbac2b444,0x3addb95f,0x3848bbb6,0x30b23b88,0x367c3a0f,0xbbea3564,0xbb50393a,0x33c6bbfe,0x3179bbf1,0x3bc32a48,0x3be2afd6,
0x3a2fbb0e,0x3303bbb6,0x3913378b,0x3bceb444,0xbbf634a5,0xbb773a0f,0x2e46bba8,0xb5c2b93a,0x3913378b,0x3a8a2fd6,0xba2f3b0e,0xb89b3bf1,
0x2e46bba8,0x2648bb25,0x3bf6b4a5,0x3bffb732,0xb6d7b81d,0xbb253303,0x3b3bbadd,0x3732bbce,0xb95f3bea,0xb4443b50,0xb9edb0b2,0xbbb6367c,
0x3b88b3c6,0x3bfab89b,0xb5643bc3,0xacb53a8a,0xaa48ba6d,0xafd6b984,0x3bfeb8c4,0x3bf1b9cb,0xbbd93aa7,0xb93a3be2,0xb23eb872,0xba0f3179,
0x323e3872,0x38ec2648,0xbbd93aa7,0xba4f3bff,0x3bd9baa7,0x3b25bbce,0x323e3872,0x37323303,0xb23eb872,0xb444b67c,0x3bd9baa7,0x3bb6bb50,
0xaa4838c4,0x389bafd6,0xbbfe3a6d,0xba8a3bf1,0x3b3bb81d,0x3bffbb25,0xb6d73add,0x26483732,0x39edbbea,0x3848baf6,0x395fb0b2,0x3ac2b7e3,
0xb564b3c6,0xb67cacb5,0x3b88bbc3,0x3b50bbfa,0x3ba8ba2f,0x3b77bbfa,0xb4a53913,0x35c2acb5,0x3b0ebbf6,0x389bba4f,0x378bae46,0x3a8ab8ec,
0x34a5b913,0x2648b505,0x3ba8ba2f,0x3bffbb99,0xb78b2e46,0xb8483444,0x3b0ebbf6,0x3ac2bbb6,0x381db95f,0xafd62648,0x3addb9ed,0x3bf1bbff,
0x30b2b564,0xb5053303,0x3beabb88,0x3b99bbce,0xb3c62a48,0xb7e3367c,0x3bc3bbfe,0x3af6bb50,0xb8c436d7,0xb93a389b,0x3a6dbb3b,0x3a0fba8a,
0xb9a839a8,0xbbf13bff,0x39a8b9a8,0x2fd6a648,0xb9a839a8,0xbb993bce,0x39a8b9a8,0x3505b303,0xb9a839a8,0xbaf63b50,0x39a8b9a8,0x37e3b67c,
0xb9a839a8,0xba0f3a8a,0x39a8b9a8,0x393ab89b,0xbadd39ed,0xb5c22cb5,0xb81d395f,0xbb773bfa,0xbbea3b88,0xba8a38ec,0xb0b23564,0xb89b3a4f,
0xbbc33bfe,0xbbff3b99,0x33c6aa48,0xa6483505,0xba6d3b3b,0xbac23bb6,0x38c4b6d7,0x3848b444,0x34a5b913,0x3a8abbf1,0xbba83a2f,0xb89b2fd6,
0xb78b2e46,0xa648b732,0xbb0e3bf6,0xbbff3b25,0xbba83a2f,0xbac237e3,0xb4a53913,0xb8483af6,0xbb0e3bf6,0xbb503bfa,0x378bae46,0x367c2cb5,
0x3bfeba6d,0x3a0fb179,0x2a48b8c4,0x393abbe2,0x36d7badd,0x3a4fbbff,0xbb3b381d,0xb8eca648,0xb95f30b2,0xb732b303,0xb9ed3bea,0xbb253bce,
0xbb883bc3,0xbbb63b50,0x356433c6,0x3444367c,0x323e3872,0xb7323bce,0x3bd9baa7,0x3b25b303,0x3bd9baa7,0x3bb6b67c,0xb23eb872,0x3444bb50,
0xb23eb872,0x2cb5ba8a,0xbbd93aa7,0xbbfa389b,0xbbd93aa7,0xbbf139cb,0x323e3872,0x2fd63984,0xbb3b3add,0xbbce3444,0x36d7381d,0xb3033bb6,
0x39ed30b2,0x35c2393a,0x395fbbea,0x3b77ba0f,0x3564bbc3,0x389bbbf1,0xbb8833c6,0xba8aafd6,0xbbfe38c4,0xbbff3732,0x2a483a6d,0xa6483b25,
0xb913b78b,0xa648bb99,0xba2f3b0e,0xbbff3505,0xae463ba8,0xb8483bb6,0x3bf6b4a5,0x3ac23444,0x3a2fbb0e,0x3b50b93a,0xb913b78b,0xb67cba0f,
0xbbf634a5,0xbbe22fd6,0xae463ba8,0xb1793bf1,0x38c4bb3b,0x3bb6b5c2,0xba6db6d7,0xb444bb77,0xbadd395f,0xbbfa3179,0x381d39ed,0x2cb53be2,
0x3beab564,0x3bf12648,0xb0b2bb88,0x2fd6bbff,0xbbc3aa48,0xbb99b303,0xb3c63bfe,0xb5053bce,0x3b64361f,0x37e33b50,0x361fbb64,0x3af6b67c,
0xbb64b61f,0xb93aba8a,0xb61f3b64,0xba0f389b,0x3b64361f,0x3a4f3984,0x361fbb64,0x38ecb9cb,0xbb64b61f,0xbb25b848,0xb61f3b64,0xb7323ac2,
0xb0b23b88,0xb9cb3732,0x3bea3564,0x39843b25,0xb3c6bbfe,0x3303baf6,0xbbc32a48,0xbbceb7e3,0x38c43b3b,0x35c23bfa,0x3a6db6d7,0x3b77acb5,
0xbaddb95f,0xba8aba4f,0xb81d39ed,0xb89b38ec,0xbbf6b4a5,0xbac2baf6,0x2e463ba8,0xb84837e3,0x3913b78b,0x3b502cb5,0xba2fbb0e,0xb67cbbfa,
0x2e463ba8,0xb1793a4f,0x3bf634a5,0x3be238ec,0xba2fbb0e,0xb9cbbb99,0xb913378b,0xb9843505,0xb564bbc3,0x3505b848,0xbb88b3c6,0xbb99bac2,
0x3bfe38c4,0x3af63b77,0x2a48ba6d,0x37e3b5c2,0xb6d7381d,0xb93a3179,0x3b3b3add,0x3a0f3be2,0xb95fbbea,0xb8ecbbff,0xb9ed30b2,0xba4fa648,
0x3aa7323e,0x3bfa3a8a,0xb872bbd9,0x2cb5b89b,0x38723bd9,0x2fd639cb,0x3aa7323e,0x3bf13984,0xbaa7b23e,0xbb99b848,0x38723bd9,0x35053ac2,
0xb872bbd9,0xb7e3bb77,0xbaa7b23e,0xbaf6b5c2,0x39ed3bea,0x317938ec,0x395f30b2,0x3be23a4f,0xb56433c6,0xb9cbb505,0x3b883bc3,0x39843b99,
0xbbfeba6d,0xbbcebbb6,0x2a4838c4,0xb3033444,0xb6d7badd,0xb5c2ba0f,0xbb3bb81d,0xbb77b93a,0xb78bae46,0xbb50ba0f,0x3b0e3bf6,0x367c393a,
0xbba8ba2f,0xbbe2bbf1,0x34a53913,0xb1792fd6,0xbb0ebbf6,0xb9cbbb25,0xb78bae46,0xb984b732,0xb4a5b913,0xb303b7e3,0xbba8ba2f,0xbbcebaf6,
0xbbc3bbfe,0xb8ecb984,0xb3c6aa48,0xba4fb9cb,0xba6dbb3b,0xb732b848,0xb8c4b6d7,0xbb25bac2,0xb81db95f,0xb444b5c2,0xbaddb9ed,0xbbb6bb77,
0xb0b2b564,0xacb5b179,0xbbeabb88,0xbbfabbe2,0x3c003c00,0x96480000,0x3c003c00,0xa311a248,0x3c003c00,0x9cb69a48,0x3c003c00,0xa452a3db,
0x3c003c00,0x9fdb9e48,0x3c003c00,0xa51ba4b6,0x3c003c00,0xa17fa0b6,0x3bff3c00,0xa5e4a57f,0x3c003c00,0x9fdb0000,0x3bfb3bfc,0xac6aabd9,
0x3bff3c00,0xa5e4a3db,0x3bf93bfa,0xad65ace7,0x3bfe3bff,0xa8e8a7da,0x3bf63bf7,0xae5fade2,0x3bfd3bfe,0xaadea9e3,0x3bf23bf4,0xaf59aedc,
0x3c003c00,0xa3110000,0x3bf03bf4,0xafefaf0e,0x3bfe3bff,0xa94da711,0x3be83bed,0xb0d7b067,0x3bfb3bfd,0xac6aab11,0x3bdf3be4,0xb1b6b147,
0x3bf63bf9,0xae2dad4c,0x3bd43bda,0xb294b226,0x3c003c00,0xa51b0000,0x3bdf3be6,0xb1b6b115,0x3bfc3bfe,0xaba7a91b,0x3bcf3bd7,0xb2f7b257,
0x3bf63bf9,0xae5fad1a,0x3bbc3bc6,0xb41ab396,0x3bec3bf1,0xb074afa4,0x3ba53bb1,0xb4b7b469,0x3bff3c00,0xa6ad0000,0x3bc83bd4,0xb371b2a1,
0x3bfa3bfd,0xad00aaac,0x3bac3bbb,0xb487b420,0x3bef3bf5,0xb029aeaa,0x3b8b3b9d,0xb552b4ed,0x3bde3be7,0xb1cfb0fd,0x3b653b79,0xb61ab5b6,
0x3bff3c00,0xa81f0000,0x3bab3bbc,0xb493b414,0x3bf63bfc,0xae2dac1f,0x3b813b97,0xb58db511,0x3be53bef,0xb122b01d,0x3b4f3b69,0xb682b608,
0x3bcc3bda,0xb328b226,0x3b163b33,0xb76fb6f9,0x3bfe3c00,0xa8e80000,0x3b873ba0,0xb56ab4d5,0x3bf23bfa,0xaf59ace7,0x3b4c3b6b,0xb68db5fd,
0x3bda3be8,0xb219b0e4,0x3b073b2b,0xb7a6b71b,0x3bb73bca,0xb43eb34c,0x3ab63ae0,0xb85ab817,0x3bfe3c00,0xa9b10000,0x3b5e3b80,0xb63cb593,
0x3bee3bf8,0xb042adb0,0x3b103b39,0xb785b6e3,0x3bce3be0,0xb30fb1aa,0x3ab33ae3,0xb85fb812,0x3b9e3bb7,0xb4e7b438,0x3a493a7f,0xb8f3b8ab,
0x3bfd3c00,0xaa7a0000,0x3b2f3b5a,0xb70ab64e,0x3be83bf6,0xb0d7ae78,0x3acb3aff,0xb83ab7c2,0x3bbf3bd6,0xb402b26f,0x3a543a92,0xb8e5b891,
0x3b813ba2,0xb58db4c9,0x39cd3a13,0xb982b935,0x3bfd3c00,0xab430000,0x3afb3b30,0xb7d2b705,0x3be23bf3,0xb16caf40,0x3a7e3abf,0xb8adb84d,
0x3bae3bcb,0xb47bb334,0x39eb3a37,0xb962b909,0x3b603b8a,0xb631b558,0x3946399b,0xba04b9b5,0x3bfc3c00,0xac060000,0x3ac13b02,0xb84ab7b7,
0x3bdc3bf0,0xb201b004,0x3a293a78,0xb91bb8b5,0x3b9c3bc0,0xb4f3b3f7,0x397939d4,0xb9d6b97b,0x3b3d3b70,0xb6d2b5e5,0x38b23918,0xba7aba2b,
0x3bfb3c00,0xac6a0000,0x3a813ad0,0xb8a8b832,0x3bd43bed,0xb294b067,0x39cd3a2b,0xb982b918,0x3b873bb2,0xb56ab45d,0x38fd3969,0xba41b9e5,
0x3b163b53,0xb76fb670,0x3815388c,0xbae1ba95,0x3bfa3c00,0xacce0000,0x3a3d3a99,0xb902b887,0x3bcc3be9,0xb328b0cb,0x396b39d8,0xb9e3b976,
0x3b713ba4,0xb5dfb4bd,0x387a38f6,0xbaa2ba47,0x3aeb3b33,0xb805b6f9,0x36dd37ee,0xbb3abaf3,0x3bf93c00,0xad330000,0x39f43a5e,0xb958b8d8,
0x3bc33be5,0xb3bab12e,0x39023980,0xba3db9d0,0x3b593b95,0xb654b51d,0x37dd387c,0xbaf7baa0,0x3abd3b11,0xb850b780,0x358136b5,0xbb83bb43,
0x3bf83c00,0xad970000,0x39a63a1f,0xb9aab927,0x3bba3be1,0xb426b191,0x38943922,0xba90ba23,0x3b3f3b84,0xb6c6b57c,0x36bb37f9,0xbb42baf0,
0x3a8c3aed,0xb899b802,0x341a3570,0xbbbcbb86,0x3bf73c00,0xadfb0000,0x395439dc,0xb9f8b972,0x3bb03bdc,0xb46fb1f4,0x382038bf,0xbadbba71,
0x3b243b72,0xb737b5da,0x358d36ee,0xbb81bb36,0x3a583ac6,0xb8e0b842,0x31533420,0xbbe3bbbb,0x3bf63c00,0xae5f0000,0x38fd3996,0xba41b9ba,
0x3ba53bd7,0xb4b7b257,0x374e3858,0xbb1ebab8,0x3b073b5f,0xb7a6b637,0x345735da,0xbbb3bb72,0x3a213a9c,0xb924b881,0x2cce3191,0xbbfabbe1,
0x3bf53c00,0xaec30000,0x38a3394d,0xba85b9fe,0x3b9a3bd2,0xb4ffb2b9,0x365437d8,0xbb59baf9,0x3ae83b4b,0xb80ab693,0x323234bd,0xbbd9bba4,
0x39e73a71,0xb966b8bf,0xa4522db0,0xbc00bbf8,0x3bf33c00,0xaf270000,0x38453900,0xbac4ba3f,0x3b8e3bcd,0xb546b31b,0x355236f9,0xbb8bbb33,
0x3ac73b36,0xb840b6ee,0x2f593334,0xbbf2bbcb,0x39aa3a43,0xb9a6b8fb,0xaef51a48,0xbbf4bc00,0x3bf23c00,0xaf8b0000,0x37c838b0,0xbafeba7c,
0x3b813bc7,0xb58db37d,0x344b3614,0xbbb5bb67,0x3aa53b20,0xb874b748,0x288430e4,0xbbffbbe8,0x396b3a13,0xb9e3b935,0xb263ad4c,0xbbd7bbf9,
0x3bf03c00,0xafef0000,0x36ff385d,0xbb32bab5,0x3b733bc1,0xb5d4b3df,0x327c3529,0xbbd6bb93,0x3a813b08,0xb8a8b7a1,0xa9b12d1a,0xbbfebbf9,
0x392939e1,0xba1db96d,0xb49fb160,0xbba9bbe3,0x3bef3c00,0xb0290000,0x36313807,0xbb60bae9,0x3b653bbb,0xb61ab420,0x305b3438,0xbbedbbb7,
0x3a5c3af0,0xb8dbb7f9,0xafef1e48,0xbbf0bc00,0x38e539ad,0xba54b9a4,0xb602b408,0xbb6abbbe,0x3bed3c00,0xb05b0000,0x355e375e,0xbb89bb1a,
0x3b573bb4,0xb65fb451,0x2c6a3288,0xbbfbbbd5,0x3a353ad6,0xb90cb828,0xb27cac51,0xbbd6bbfb,0x389e3976,0xba89b9d8,0xb759b558,0xbb1bbb8a,
0x3beb3c00,0xb08d0000,0x348736aa,0xbbacbb46,0x3b473bad,0xb6a4b481,0x16483099,0xbc00bbeb,0x3a0d3abc,0xb93cb852,0xb47bb080,0xbbaebbec,
0x3855393e,0xbababa0b,0xb850b69e,0xbabdbb49,0x3be93c00,0xb0be0000,0x335935f1,0xbbc9bb6e,0x3b373ba6,0xb6e8b4b1,0xac382d4c,0xbbfcbbf9,
0x39e33aa0,0xb96bb87c,0xb5b1b2d2,0xbb7abbd1,0x380a3905,0xbae8ba3b,0xb8eab7d8,0xba50baf9,0x3be73c00,0xb0f00000,0x319e3534,0xbbe0bb91,
0x3b273b9e,0xb72cb4e1,0xb042257f,0xbbeebc00,0x39b83a83,0xb999b8a6,0xb6ddb48d,0xbb3abbab,0x377a38c9,0xbb13ba69,0xb979b881,0xb9d6ba9c,
0x3be53c00,0xb1220000,0x2fbd3475,0xbbf1bbaf,0x3b163b97,0xb76fb511,0xb263a91b,0xbbd7bbfe,0x398b3a65,0xb9c5b8ce,0xb7feb5ab,0xbaeebb7b,
0x36dd388c,0xbb3aba95,0xb9fcb90e,0xb94fba33,0x3be33c00,0xb1530000,0x2c383365,0xbbfcbbc9,0x3b043b8f,0xb7b2b540,0xb43eae78,0xbbb7bbf6,
0x395d3a47,0xb9f0b8f6,0xb889b6c1,0xba97bb41,0x363c384d,0xbb5ebabf,0xba73b992,0xb8bcb9be,0x3be13c00,0xb1850000,0x217f31db,0xbc00bbdd,
0x3af13b86,0xb7f3b570,0xb546b12e,0xbb8ebbe5,0x392e3a27,0xba19b91d,0xb90cb7cd,0xba35bafc,0x3599380d,0xbb7fbae6,0xbadbba0b,0xb820b93e,
0x3bdf3c00,0xb1b60000,0xa9b1304e,0xbbfebbed,0x3ade3b7d,0xb81ab59f,0xb648b31b,0xbb5cbbcd,0x38fd3a07,0xba41b943,0xb986b867,0xb9c9baae,
0x34f33796,0xbb9cbb0b,0xbb35ba78,0xb6f4b8b5,0x3bdd3c00,0xb1e80000,0xae5f2d7e,0xbbf6bbf8,0x3acb3b74,0xb83ab5ce,0xb742b481,0xbb21bbad,
0x38cc39e5,0xba67b969,0xb9f8b8e2,0xb954ba56,0x344b3710,0xbbb5bb2e,0xbb7fbad9,0xb599b822,0x3bda3c00,0xb2190000,0xb0f028b6,0xbbe7bbff,
0x3ab63b6b,0xb85ab5fd,0xb81ab570,0xbadebb86,0x389939c3,0xba8cb98d,0xba60b956,0xb8d6b9f6,0x33403687,0xbbcbbb4e,0xbbb8bb2e,0xb432b710,
0x3bff3bff,0xa6ada648,0x3bfe3bff,0xa8e8a8b6,0x3bff3bff,0xa776a711,0x3bfe3bfe,0xa94da91b,0x3bff3bff,0xa81fa7da,0x3bfe3bfe,0xa9b1a97f,
0x3bff3bff,0xa884a852,0x3bfe3bfe,0xaa16a9e3,0x3bef3bf1,0xb029afd6,0x3bda3bdd,0xb219b1db,0x3bea3bed,0xb0a6b067,0x3bd43bd7,0xb294b257,
0x3be53be8,0xb122b0e4,0x3bce3bd1,0xb30fb2d2,0x3be03be3,0xb19eb160,0x3bc63bca,0xb389b34c,0x3bc83bce,0xb371b303,0x3b873b91,0xb56ab534,
0x3bba3bc1,0xb426b3df,0x3b733b7d,0xb5d4b59f,0x3bab3bb2,0xb493b45d,0x3b5e3b69,0xb63cb608,0x3b9a3ba2,0xb4ffb4c9,0x3b473b53,0xb6a4b670,
0x3b8b3b99,0xb552b505,0x3b073b1a,0xb7a6b75e,0x3b6f3b7d,0xb5ebb59f,0x3ade3af3,0xb81ab7ee,0x3b4f3b5f,0xb682b637,0x3ab33ac9,0xb85fb83d,
0x3b2c3b3e,0xb715b6cc,0x3a853a9c,0xb8a3b881,0x3b3a3b50,0xb6ddb67c,0x3a5c3a7c,0xb8dbb8b0,0x3b0a3b22,0xb79bb73d,0x3a193a3b,0xb92eb905,
0x3ad53af0,0xb82ab7f9,0x39d239f6,0xb97db956,0x3a9b3ab8,0xb884b858,0x398639ad,0xb9c9b9a4,0x3ad53af6,0xb82ab7e3,0x398b39ba,0xb9c5b996,
0x3a8c3ab1,0xb899b862,0x3929395b,0xba1db9f2,0x3a3d3a65,0xb902b8ce,0x38c138f6,0xba6fba47,0x39e73a13,0xb966b935,0x3855388c,0xbababa95,
0x3a5c3a8a,0xb8dbb89b,0x389938d8,0xba8cba5e,0x39f83a2b,0xb954b918,0x38153858,0xbae1bab8,0x398b39c3,0xb9c5b98d,0x371537a1,0xbb2cbb08,
0x39163951,0xba2db9fa,0x35f73687,0xbb6cbb4e,0x39d23a0f,0xb97db93a,0x371537b7,0xbb2cbb02,0x394f3992,0xb9fcb9be,0x35c83670,0xbb76bb53,
0x38c13909,0xba6fba37,0x346f351d,0xbbb0bb95,0x382a3877,0xbad5baa3,0x3219337d,0xbbdabbc7,0x39373984,0xba11b9cb,0x34cf3593,0xbba1bb80,
0x389438e7,0xba90ba52,0x327c3408,0xbbd6bbbe,0x37c8383d,0xbafebac9,0x2e9130e4,0xbbf5bbe8,0x36543710,0xbb59bb2e,0x16482aac,0xbc00bbfd,
0x388e38ec,0xba93ba4f,0x30d732a1,0xbbe8bbd4,0x3790382d,0xbb0dbad3,0x28e82e14,0xbbfebbf7,0x35eb36c1,0xbb6fbb41,0xaccea4b6,0xbbfabc00,
0x34323511,0xbbb8bb97,0xb201b036,0xbbdcbbee,0x37b23848,0xbb04bac2,0x96482bd9,0xbc00bbfc,0x35df36cc,0xbb71bb3e,0xb010ac1f,0xbbefbbfc,
0x33eb34ed,0xbbc0bb9d,0xb402b20d,0xbbbfbbdb,0x2fef31f4,0xbbf0bbdc,0xb5ebb4f9,0xbb6fbb9b,0x36313732,0xbb60bb25,0xb0f0ad7e,0xbbe7bbf8,
0x341a3529,0xbbbcbb93,0xb49fb31b,0xbba9bbcd,0x2fbd320d,0xbbf1bbdb,0xb6afb5ab,0xbb45bb7b,0xa4522aac,0xbc00bbfd,0xb850b7ac,0xbabdbb05,
0x349f35c2,0xbba9bb77,0xb4dbb365,0xbb9fbbc9,0x308d32ea,0xbbebbbd0,0xb715b5fd,0xbb2cbb6b,0x9fdb2c51,0xbc00bbfb,0xb894b812,0xba90bae3,
0xb109ad4c,0xbbe6bbf9,0xb982b90e,0xb9cdba33,0x32013444,0xbbdcbbb6,0xb721b5f1,0xbb2abb6e,0x26ad2edc,0xbbffbbf4,0xb8adb822,0xba7ebad9,
0xb05bab11,0xbbedbbfd,0xb9aab930,0xb9a6ba17,0xb4b7b2ea,0xbba5bbd0,0xba81ba1b,0xb8a8b92b,0x2d653179,0xbbf9bbe2,0xb89eb807,0xba89bae9,
0xadc99a48,0xbbf8bc00,0xb9afb92b,0xb9a1ba1b,0xb432b1aa,0xbbb8bbe0,0xba93ba27,0xb88eb91d,0xb6d2b587,0xbb3dbb82,0xbb45baf3,0xb6afb7ee,
0xa51b2cb5,0xbc00bbfa,0xb990b900,0xb9c0ba3f,0xb294af40,0xbbd4bbf3,0xba89ba13,0xb89eb935,0xb625b4bd,0xbb63bba4,0xbb47baf0,0xb6a4b7f9,
0xb865b780,0xbab0bb11,0xbbc5bb8f,0xb3a2b540,0xafefa648,0xbbf0bbff,0xba60b9dc,0xb8d6b972,0xb517b31b,0xbb96bbcd,0xbb35bad3,0xb6f4b82d,
0xb7feb693,0xbaeebb4b,0xbbc0bb84,0xb3ebb57c,0xb94ab8ab,0xba00ba7f,0xbbfdbbe9,0xaa7ab0cb,0xb340afd6,0xbbcbbbf1,0xbb0aba99,0xb79bb887,
0xb6d2b540,0xbb3dbb8f,0xbbaebb67,0xb47bb614,0xb8dbb828,0xba5cbad6,0xbbfbbbe0,0xac9cb1aa,0xba15b980,0xb933b9d0,0xbbecbbff,0x30742852,
0xb53ab303,0xbb90bbce,0xbb89bb30,0xb55eb705,0xb83ab6e3,0xbacbbb39,0xbbf2bbca,0xaf8bb34c,0xb9a1b8f6,0xb9afba47,0xbbf5bc00,0x2ec39e48,
0xbac1ba3b,0xb84ab905,0xbb92bbd0,0x352f32ea,0xb6c6b505,0xbb3fbb99,0xbbdcbba0,0xb201b4d5,0xb8fdb838,0xba41bacc,0xbbfebbfb,0x2a16ac83,
0xba50b9b1,0xb8eab99f,0xbbaebbe4,0x347b3147,0xbb4abad9,0xb699b822,0xbaf1bb5d,0x37f33642,0xb820b67c,0xbadbbb50,0xbbffbbe6,0xa884b115,
0xb9afb8f1,0xb9a1ba4b,0xbbd2bbf8,0x32c62db0,0xbae5ba56,0xb80fb8e2,0xbb2abb8c,0x3721354c,0xbbaebb58,0xb47bb659,0xba11baaa,0x3937386d,
0xb8d1b7e3,0xba64baf6,0xbbf2bc00,0x2f8ba248,0xba4db99b,0xb8eeb9b5,0xbb6fbbc1,0x35eb33df,0xbb5cbae3,0xb648b812,0xba6bbafc,0x38c737cd,
0xbbebbbb4,0xb08db451,0xb8f8b9be,0x3a453992,0xb974b89b,0xb9daba8a,0xbbb5bbed,0x344b304e,0xbad5ba33,0xb82ab90e,0xbad8bb58,0x38253659,
0xbbb3bb55,0xb457b665,0xb979ba37,0x39d63909,0xbc00bbed,0x9648b067,0xb764b8a0,0x3b183a87,0xba09b93a,0xb941ba0f,0xbb4abbaf,0x36993475,
0xbb45bab8,0xb6afb858,0xba11babf,0x3937384d,0xbbeabbab,0xb0a6b48d,0xb85ab943,0x3ab63a07,0xbbecbc00,0x30749a48,0xb493b6b5,0x3bab3b43,
0xba8cb9cb,0xb899b984,0xbab3bb46,0x385f36aa,0xbb9cbb28,0xb4f3b726,0xb91fb9fa,0x3a253951,0xbc00bbe4,0xa452b147,0xb631b828,0x3b603ad6,
0xbbb0bbee,0x346f3036,0xae5fb3df,0x3bf63bc1,0xbafeba4f,0xb7c8b8ec,0xb9f4bab5,0x3958385d,0xbbd8bb82,0xb24bb587,0xb80ab90e,0x3ae83a33,
0xbbf3bbfe,0x2f27a97f,0xb2f7b5da,0x3bcf3b72,0xbb4cbbb7,0x368d3438,0x2dc9ac1f,0x3bf83bfc,0xbb5cbac2,0xb648b848,0xb911b9fe,0x3a31394d,
0xbbf9bbc4,0xad33b3ae,0xb5b1b802,0x3b7a3aed,0xbbc5bbf9,0x33a22d1a,0xa94db26f,0x3bfe3bd6,0xbac4bb5d,0x38453642,0x346f2fa4,0x3bb03bf1,
0xbba5bb25,0xb4b7b732,0xb80fb927,0x3ae53a1f,0xbbffbbee,0x2884b036,0xb24bb5b6,0x3bd83b79,0xbb76bbd6,0x35c8326f,0x305ba7da,0x3bed3bff,
0xba19bae0,0x392e3817,0x374234c9,0x3b213ba2,0xbbd9bb77,0xb232b5c2,0xb5ebb832,0x3b6f3ad0,0xbbe8bc00,0x30d7a57f,0xa81fb288,0x3bff3bd5,
0xbb07bb95,0x37a6351d,0x34f33080,0x3b9c3bec,0xb94fba43,0x39fc38fb,0x38ea3780,0x3a503b11,0xbbf8bbb6,0xadc9b444,0xb328b64e,0x3bcc3b5a,
0xbbb7bbf8,0x343e2db0,0x3042a9e3,0x3bee3bfe,0xba7abb36,0x38b236ee,0x379034ed,0x3b0d3b9d,0xb86ab989,0x3aac39c7,0x3a0438fb,0x39463a43,
0xbc00bbe2,0x2311b179,0xac9cb414,0x3bfb3bbc,0xbb6abbd7,0x36023257,0x34b72f40,0x3ba53bf3,0xb9d2babc,0x397d3852,0x38f83775,0x3a453b14,
0xb6ddb8b5,0x3b3a3a78,0x3ae83a0b,0x380a393e,0xbbf2bbfa,0x2f8bacb5,0x2d33af0e,0x3bf93bf4,0xbb04bb9e,0x37b234e1,0x372c3451,0x3b273bb4,
0xb911ba27,0x3a31391d,0x3a0038e2,0x394a3a56,0xb4c3b796,0x3ba33b0b,0x3b8b3ae6,0x3552380d,0x4c004c00,0x26480000,0x4c004c00,0x33113248,
0x4c004c00,0x2cb62a48,0x4c004c00,0x345233db,0x4c004c00,0x2fdb2e48,0x4c004c00,0x351b34b6,0x4c004c00,0x317f30b6,0x4bff4c00,0x35e4357f,
0x4c004c00,0x2fdb0000,0x4bfb4bfc,0x3c6a3bd9,0x4bff4c00,0x35e433db,0x4bf94bfa,0x3d653ce7,0x4bfe4bff,0x38e837da,0x4bf64bf7,0x3e5f3de2,
0x4bfd4bfe,0x3ade39e3,0x4bf24bf4,0x3f593edc,0x4c004c00,0x33110000,0x4bf04bf4,0x3fef3f0e,0x4bfe4bff,0x394d3711,0x4be84bed,0x40d74067,
0x4bfb4bfd,0x3c6a3b11,0x4bdf4be4,0x41b64147,0x4bf64bf9,0x3e2d3d4c,0x4bd44bda,0x42944226,0x4c004c00,0x351b0000,0x4bdf4be6,0x41b64115,
0x4bfc4bfe,0x3ba7391b,0x4bcf4bd7,0x42f74257,0x4bf64bf9,0x3e5f3d1a,0x4bbc4bc6,0x441a4396,0x4bec4bf1,0x40743fa4,0x4ba54bb1,0x44b74469,
0x4bff4c00,0x36ad0000,0x4bc84bd4,0x437142a1,0x4bfa4bfd,0x3d003aac,0x4bac4bbb,0x44874420,0x4bef4bf5,0x40293eaa,0x4b8b4b9d,0x455244ed,
0x4bde4be7,0x41cf40fd,0x4b654b79,0x461a45b6,0x4bff4c00,0x381f0000,0x4bab4bbc,0x44934414,0x4bf64bfc,0x3e2d3c1f,0x4b814b97,0x458d4511,
0x4be54bef,0x4122401d,0x4b4f4b69,0x46824608,0x4bcc4bda,0x43284226,0x4b164b33,0x476f46f9,0x4bfe4c00,0x38e80000,0x4b874ba0,0x456a44d5,
0x4bf24bfa,0x3f593ce7,0x4b4c4b6b,0x468d45fd,0x4bda4be8,0x421940e4,0x4b074b2b,0x47a6471b,0x4bb74bca,0x443e434c,0x4ab64ae0,0x485a4817,
0x4bfe4c00,0x39b10000,0x4b5e4b80,0x463c4593,0x4bee4bf8,0x40423db0,0x4b104b39,0x478546e3,0x4bce4be0,0x430f41aa,0x4ab34ae3,0x485f4812,
0x4b9e4bb7,0x44e74438,0x4a494a7f,0x48f348ab,0x4bfd4c00,0x3a7a0000,0x4b2f4b5a,0x470a464e,0x4be84bf6,0x40d73e78,0x4acb4aff,0x483a47c2,
0x4bbf4bd6,0x4402426f,0x4a544a92,0x48e54891,0x4b814ba2,0x458d44c9,0x49cd4a13,0x49824935,0x4bfd4c00,0x3b430000,0x4afb4b30,0x47d24705,
0x4be24bf3,0x416c3f40,0x4a7e4abf,0x48ad484d,0x4bae4bcb,0x447b4334,0x49eb4a37,0x49624909,0x4b604b8a,0x46314558,0x4946499b,0x4a0449b5,
0x4bfc4c00,0x3c060000,0x4ac14b02,0x484a47b7,0x4bdc4bf0,0x42014004,0x4a294a78,0x491b48b5,0x4b9c4bc0,0x44f343f7,0x497949d4,0x49d6497b,
0x4b3d4b70,0x46d245e5,0x48b24918,0x4a7a4a2b,0x4bfb4c00,0x3c6a0000,0x4a814ad0,0x48a84832,0x4bd44bed,0x42944067,0x49cd4a2b,0x49824918,
0x4b874bb2,0x456a445d,0x48fd4969,0x4a4149e5,0x4b164b53,0x476f4670,0x4815488c,0x4ae14a95,0x4bfa4c00,0x3cce0000,0x4a3d4a99,0x49024887,
0x4bcc4be9,0x432840cb,0x496b49d8,0x49e34976,0x4b714ba4,0x45df44bd,0x487a48f6,0x4aa24a47,0x4aeb4b33,0x480546f9,0x46dd47ee,0x4b3a4af3,
0x4bf94c00,0x3d330000,0x49f44a5e,0x495848d8,0x4bc34be5,0x43ba412e,0x49024980,0x4a3d49d0,0x4b594b95,0x4654451d,0x47dd487c,0x4af74aa0,
0x4abd4b11,0x48504780,0x458146b5,0x4b834b43,0x4bf84c00,0x3d970000,0x49a64a1f,0x49aa4927,0x4bba4be1,0x44264191,0x48944922,0x4a904a23,
0x4b3f4b84,0x46c6457c,0x46bb47f9,0x4b424af0,0x4a8c4aed,0x48994802,0x441a4570,0x4bbc4b86,0x4bf74c00,0x3dfb0000,0x495449dc,0x49f84972,
0x4bb04bdc,0x446f41f4,0x482048bf,0x4adb4a71,0x4b244b72,0x473745da,0x458d46ee,0x4b814b36,0x4a584ac6,0x48e04842,0x41534420,0x4be34bbb,
0x4bf64c00,0x3e5f0000,0x48fd4996,0x4a4149ba,0x4ba54bd7,0x44b74257,0x474e4858,0x4b1e4ab8,0x4b074b5f,0x47a64637,0x445745da,0x4bb34b72,
0x4a214a9c,0x49244881,0x3cce4191,0x4bfa4be1,0x4bf54c00,0x3ec30000,0x48a3494d,0x4a8549fe,0x4b9a4bd2,0x44ff42b9,0x465447d8,0x4b594af9,
0x4ae84b4b,0x480a4693,0x423244bd,0x4bd94ba4,0x49e74a71,0x496648bf,0xb4523db0,0x4c004bf8,0x4bf34c00,0x3f270000,0x48454900,0x4ac44a3f,
0x4b8e4bcd,0x4546431b,0x455246f9,0x4b8b4b33,0x4ac74b36,0x484046ee,0x3f594334,0x4bf24bcb,0x49aa4a43,0x49a648fb,0xbef52a48,0x4bf44c00,
0x4bf24c00,0x3f8b0000,0x47c848b0,0x4afe4a7c,0x4b814bc7,0x458d437d,0x444b4614,0x4bb54b67,0x4aa54b20,0x48744748,0x388440e4,0x4bff4be8,
0x496b4a13,0x49e34935,0xc263bd4c,0x4bd74bf9,0x4bf04c00,0x3fef0000,0x46ff485d,0x4b324ab5,0x4b734bc1,0x45d443df,0x427c4529,0x4bd64b93,
0x4a814b08,0x48a847a1,0xb9b13d1a,0x4bfe4bf9,0x492949e1,0x4a1d496d,0xc49fc160,0x4ba94be3,0x4bef4c00,0x40290000,0x46314807,0x4b604ae9,
0x4b654bbb,0x461a4420,0x405b4438,0x4bed4bb7,0x4a5c4af0,0x48db47f9,0xbfef2e48,0x4bf04c00,0x48e549ad,0x4a5449a4,0xc602c408,0x4b6a4bbe,
0x4bed4c00,0x405b0000,0x455e475e,0x4b894b1a,0x4b574bb4,0x465f4451,0x3c6a4288,0x4bfb4bd5,0x4a354ad6,0x490c4828,0xc27cbc51,0x4bd64bfb,
0x489e4976,0x4a8949d8,0xc759c558,0x4b1b4b8a,0x4beb4c00,0x408d0000,0x448746aa,0x4bac4b46,0x4b474bad,0x46a44481,0x26484099,0x4c004beb,
0x4a0d4abc,0x493c4852,0xc47bc080,0x4bae4bec,0x4855493e,0x4aba4a0b,0xc850c69e,0x4abd4b49,0x4be94c00,0x40be0000,0x435945f1,0x4bc94b6e,
0x4b374ba6,0x46e844b1,0xbc383d4c,0x4bfc4bf9,0x49e34aa0,0x496b487c,0xc5b1c2d2,0x4b7a4bd1,0x480a4905,0x4ae84a3b,0xc8eac7d8,0x4a504af9,
0x4be74c00,0x40f00000,0x419e4534,0x4be04b91,0x4b274b9e,0x472c44e1,0xc042357f,0x4bee4c00,0x49b84a83,0x499948a6,0xc6ddc48d,0x4b3a4bab,
0x477a48c9,0x4b134a69,0xc979c881,0x49d64a9c,0x4be54c00,0x41220000,0x3fbd4475,0x4bf14baf,0x4b164b97,0x476f4511,0xc263b91b,0x4bd74bfe,
0x498b4a65,0x49c548ce,0xc7fec5ab,0x4aee4b7b,0x46dd488c,0x4b3a4a95,0xc9fcc90e,0x494f4a33,0x4be34c00,0x41530000,0x3c384365,0x4bfc4bc9,
0x4b044b8f,0x47b24540,0xc43ebe78,0x4bb74bf6,0x495d4a47,0x49f048f6,0xc889c6c1,0x4a974b41,0x463c484d,0x4b5e4abf,0xca73c992,0x48bc49be,
0x4be14c00,0x41850000,0x317f41db,0x4c004bdd,0x4af14b86,0x47f34570,0xc546c12e,0x4b8e4be5,0x492e4a27,0x4a19491d,0xc90cc7cd,0x4a354afc,
0x4599480d,0x4b7f4ae6,0xcadbca0b,0x4820493e,0x4bdf4c00,0x41b60000,0xb9b1404e,0x4bfe4bed,0x4ade4b7d,0x481a459f,0xc648c31b,0x4b5c4bcd,
0x48fd4a07,0x4a414943,0xc986c867,0x49c94aae,0x44f34796,0x4b9c4b0b,0xcb35ca78,0x46f448b5,0x4bdd4c00,0x41e80000,0xbe5f3d7e,0x4bf64bf8,
0x4acb4b74,0x483a45ce,0xc742c481,0x4b214bad,0x48cc49e5,0x4a674969,0xc9f8c8e2,0x49544a56,0x444b4710,0x4bb54b2e,0xcb7fcad9,0x45994822,
0x4bda4c00,0x42190000,0xc0f038b6,0x4be74bff,0x4ab64b6b,0x485a45fd,0xc81ac570,0x4ade4b86,0x489949c3,0x4a8c498d,0xca60c956,0x48d649f6,
0x43404687,0x4bcb4b4e,0xcbb8cb2e,0x44324710,0x4bd84c00,0x424b0000,0xc2adb248,0x4bd34c00,0x4aa24b62,0x487a462b,0xc88ec659,0x4a934b58,
0x4865499f,0x4ab049b1,0xcabdc9c3,0x4850498d,0x41e845fd,0x4bdd4b6b,0xcbe1cb74,0x418545ce,0x4bd64c00,0x427c0000,0xc432bbd9,0x4bb84bfc,
0x4a8c4b58,0x48994659,0xc8fdc73d,0x4a414b22,0x4830497b,0x4ad149d4,0xcb10ca27,0x4785491d,0x408d4570,0x4beb4b86,0xcbf9cbad,0x3d334481,
0x4bd34c00,0x42ad0000,0xc50bbf0e,0x4b984bf4,0x4a764b4e,0x48b74687,0xc966c80d,0x49e74ae6,0x47f34956,0x4af149f6,0xcb57ca83,0x465f48a6,
0x3e5f44e1,0x4bf64b9e,0xcc00cbd7,0xb17f4257,0x4bd04c00,0x42de0000,0xc5dfc115,0x4b714be6,0x4a604b43,0x48d646b5,0xc9c9c877,0x49864aa3,
0x47854930,0x4b104a17,0xcb92cad6,0x452f4828,0x3b434451,0x4bfd4bb4,0xcbf5cbf3,0xbe913f40,0x4bce4c00,0x430f0000,0xc6afc2a1,0x4b454bd4,
0x4a494b39,0x48f346e3,0xca25c8dd,0x491f4a5a,0x47154909,0x4b2c4a37,0xcbc0cb20,0x43eb4748,0x3311437d,0x4c004bc7,0xcbd9cbff,0xc2323711,
0x4bcb4c00,0x43400000,0xc77ac414,0x4b134bbc,0x4a314b2e,0x49114710,0xca7ac93e,0x48b24a0b,0x46a448e2,0x4b474a56,0xcbe2cb5f,0x416c4637,
0xb7764257,0x4bff4bd7,0xcbaccbfd,0xc487bb75,0x4bc84c00,0x43710000,0xc820c4d5,0x4adb4ba0,0x4a194b22,0x492e473d,0xcac7c99b,0x484049b5,
0x463148ba,0x4b604a74,0xcbf8cb95,0x3dc9451d,0xbc9c412e,0x4bfb4be5,0xcb6fcbeb,0xc5ebc099,0x4bc54c00,0x43a20000,0xc87fc593,0x4a9e4b80,
0x4a004b17,0x494a476a,0xcb0dc9f2,0x4790495b,0x45bc4891,0x4b784a92,0xcc00cbc0,0x317f43f7,0xbf594004,0x4bf24bf0,0xcb21cbca,0xc742c34c,
0x4bc24c00,0x43d30000,0xc8dbc64e,0x4a5c4b5a,0x49e74b0b,0x49664796,0xcb4aca43,0x469948fb,0x45464867,0x4b8e4aae,0xcbfbcbe0,0xbc6a41aa,
0xc1093db0,0x4be64bf8,0xcac4cb9b,0xc845c4f9,0x4bbf4c00,0x44020000,0xc933c705,0x4a154b30,0x49cd4aff,0x498247c2,0xcb7fca8e,0x45994896,
0x44cf483d,0x4ba14ac9,0xcbe9cbf5,0xc0be3eaa,0xc2633aac,0x4bd74bfd,0xca58cb5d,0xc8e0c642,0x4bbc4c00,0x441a0000,0xc986c7b7,0x49c94b02,
0x49b34af3,0x499d47ee,0xcbabcad3,0x4493482d,0x44574812,0x4bb34ae3,0xcbcbcbff,0xc34037da,0xc3ba33db,0x4bc34c00,0xc9dfcb11,0xc970c780,
0x4bb84c00,0x44320000,0xc9d6c832,0x49794ad0,0x49994ae6,0x49b8480d,0xcbcecb11,0x430f4780,0x43ba47cd,0x4bc34afc,0xcb9fcbfe,0xc4dbb97f,
0xc487b57f,0x4bac4c00,0xc958cab8,0xc9f4c858,0x4bb54c00,0x444b0000,0xca21c887,0x49244a99,0x497d4ad9,0x49d24822,0xcbe7cb49,0x40f0469e,
0x42c64775,0x4bd24b14,0xcb68cbf2,0xc60ebf72,0xc52fbb75,0x4b924bfd,0xc8c7ca52,0xca6bc8e7,0x4bb24c00,0x44630000,0xca67c8d8,0x48cc4a5e,
0x49624acc,0x49eb4838,0xcbf8cb79,0x3d9745b6,0x41cf471b,0x4bde4b2b,0xcb24cbdb,0xc737c20d,0xc5d4be14,0x4b734bf7,0xc82ac9e1,0xcad5c96d,
0x4bae4c00,0x447b0000,0xcaa9c927,0x486f4a1f,0x49464abf,0x4a04484d,0xcc00cba2,0x351b44c9,0x40d746c1,0x4be84b41,0xcad5cbb9,0xc82ac42c,
0xc676c036,0x4b524bee,0xc70ac964,0xcb2fc9e9,0x4bab4c00,0x44930000,0xcae5c972,0x480f49dc,0x49294ab1,0x4a1d4862,0xcbfecbc4,0xba1643ae,
0x3fbd4665,0x4bf14b55,0xca7acb8c,0xc8b2c54c,0xc715c160,0x4b2c4be3,0xc5b1c8dd,0xcb7aca5a,0x4ba74c00,0x44ab0000,0xcb1bc9ba,0x47594996,
0x490c4aa3,0x4a354877,0xcbf2cbdf,0xbf5941c3,0x3dc94608,0x4bf84b69,0xca15cb55,0xc933c665,0xc7b2c288,0x4b044bd5,0xc44bc84d,0xcbb5cabf,
0x4ba34c00,0x44c30000,0xcb4cc9fe,0x468d494d,0x48ee4a95,0x4a4d488c,0xcbdecbf1,0xc1cf3fa4,0x3ba745ab,0x4bfc4b7b,0xc9a6cb14,0xc9aac775,
0xc825c3ae,0x4ad84bc4,0xc1b6c76a,0xcbdfcb17,0x4b9f4c00,0x44db0000,0xcb78ca3f,0x45bc4900,0x48d14a87,0x4a6448a0,0xcbc0cbfd,0xc3eb3b75,
0x3776454c,0x4bff4b8c,0xc92ecac9,0xca19c83d,0xc86fc469,0x4aa94bb1,0xbd97c62b,0xcbf8cb62,0x4b9c4c00,0x44f30000,0xcb9eca7c,0x44e748b0,
0x48b24a78,0x4a7a48b5,0xcb9acc00,0xc4ffaa48,0xa64844ed,0x4c004b9d,0xc8adca74,0xca7ec8ba,0xc8b7c4f9,0x4a764b9b,0x2cb6c4e1,0xcc00cb9e,
0x4b984c00,0x450b0000,0xcbbdcab5,0x440e485d,0x48944a69,0x4a9048c9,0xcb6acbfc,0xc602bc1f,0xb81f448d,0x4bff4bab,0xc825ca17,0xcad8c930,
0xc8fdc587,0x4a414b82,0x3e2dc31b,0xcbf6cbcd,0x4b944c00,0x45230000,0xcbd7cae9,0x42634807,0x48744a5a,0x4aa548dd,0xcb32cbf0,0xc6ffc004,
0xbc06442c,0x4bfc4bb9,0xc72cc9b1,0xcb27c99f,0xc941c614,0x4a094b67,0x4201c067,0xcbdccbed,0x4b904c00,0x453a0000,0xcbeacb1a,0x40a6475e,
0x48554a4b,0x4aba48f1,0xcaf1cbdc,0xc7f3c1f4,0xbdfb4396,0x4bf74bc6,0xc602c943,0xcb6aca07,0xc982c69e,0x49cd4b49,0x446fbaac,0xcbb0cbfd,
0x4b8b4c00,0x45520000,0xcbf8cb46,0x3dc946aa,0x48354a3b,0x4ace4905,0xcaa9cbc1,0xc86fc3df,0xbfef42d2,0x4bf04bd1,0xc4cfc8ce,0xcba1ca65,
0xc9c0c726,0x49904b28,0x45d43852,0xcb73cbff,0x4b874c00,0x456a0000,0xcbffcb6e,0x388445f1,0x48154a2b,0x4ae14918,0xca58cb9e,0xc8e0c4e1,
0xc0f0420d,0x4be74bdb,0xc328c852,0xcbcccabc,0xc9fcc7ac,0x494f4b05,0x472c3fa4,0xcb27cbf1,0x4b834c00,0x45810000,0xcc00cb91,0xb51b4534,
0x47e84a1b,0x4af4492b,0xca00cb74,0xc94ac5ce,0xc1e84147,0x4bdd4be4,0xc0a6c7a1,0xcbeacb08,0xca35c817,0x490c4ae0,0x483a4288,0xcacbcbd5,
0x4b7f4c00,0x45990000,0xcbfacbaf,0xbcce4475,0x47a64a0b,0x4b07493e,0xc9a1cb43,0xc9afc6b5,0xc2de4080,0x4bd04bec,0xbc38c693,0xcbfccb4b,
0xca6bc858,0x48c74ab8,0x48d64499,0xca60cbaa,0x4b7a4c00,0x45b10000,0xcbefcbc9,0xc0294365,0x476449fa,0x4b184951,0xc93ccb0b,0xca0dc796,
0xc3d33f72,0x4bc24bf2,0x3311c57c,0xcc00cb84,0xca9ec896,0x487f4a8e,0x496645e5,0xc9e7cb70,0x4b764c00,0x45c80000,0xcbddcbdd,0xc1e841db,
0x472149e9,0x4b2a4964,0xc8d1cacc,0xca64c838,0xc4633de2,0x4bb24bf7,0x3dfbc45d,0xcbf7cbb2,0xcacec8d3,0x48354a62,0x49eb4726,0xc962cb28,
0x4b714c00,0x45df0000,0xcbc5cbed,0xc3a2404e,0x46dd49d8,0x4b3a4976,0xc85fca87,0xcab3c8a0,0xc4db3c51,0x4b9f4bfb,0x4185c26f,0xcbe1cbd6,
0xcafbc90e,0x47d24a33,0x4a64482d,0xc8d1cad3,0x4b6c4c00,0x45f70000,0xcba7cbf8,0xc4ab3d7e,0x469949c7,0x4b4a4989,0xc7d2ca3b,0xcafbc905,
0xc552397f,0x4b8b4bfe,0x4402c01d,0xcbbfcbef,0xcb24c948,0x47374a02,0x4ace48bf,0xc835ca71,0x4b684c00,0x460e0000,0xcb83cbff,0xc58138b6,
0x465449b5,0x4b59499b,0xc6ddc9e9,0xcb3ac964,0xc5c834b6,0x4b764c00,0x453abb11,0xcb90cbfd,0xcb4ac980,0x469949d0,0x4b2a4948,0xc721ca02,
0x2c002c00,0x2c002c00,0x2c002c00,0x2c002c00,0x2b642c00,0x261f29a8,0xa61f0000,0xab64a9a8,0x29a82c00,0xa9a80000,0xa9a8ac00,0x29a80000,
0x261f2c00,0xab64a9a8,0x2b640000,0xa61f29a8,0x2c00,0xac00,0x2c00,0xac00,0xa61f2c00,0x2b64a9a8,0xab640000,0x261f29a8,
0xa9a82c00,0x29a80000,0x29a8ac00,0xa9a80000,0xab642c00,0xa61f29a8,0x261f0000,0x2b64a9a8,0,0,0,0,
0x261f0000,0x2b6429a8,0x2b642c00,0x261f29a8,0x29a80000,0x29a82c00,0xa9a80000,0xa9a8ac00,0x2b640000,0xa61f29a8,0xa61fac00,0x2b6429a8,
0x2c000000,0xac000000,0x2c000000,0xac000000,0x2b640000,0xa61fa9a8,0xa61f2c00,0x2b64a9a8,0x29a80000,0x29a8ac00,0xa9a80000,0xa9a82c00,
0x261f0000,0x2b64a9a8,0x2b64ac00,0x261fa9a8,0xac002c00,0xac002c00,0xac002c00,0xac002c00,0xab642c00,0xa61f29a8,0x261f0000,0x2b64a9a8,
0xa9a82c00,0x29a80000,0x29a8ac00,0xa9a80000,0xa61f2c00,0x2b64a9a8,0xab640000,0x261f29a8,0x2c00,0xac00,0x2c00,0xac00,
0x261f2c00,0xab64a9a8,0x2b640000,0xa61f29a8,0x29a82c00,0xa9a80000,0xa9a8ac00,0x29a80000,0x2b642c00,0x261f29a8,0xa61f0000,0xab64a9a8,
0,0,0,0,0xa61f0000,0xab6429a8,0xab642c00,0xa61f29a8,0xa9a80000,0xa9a82c00,0x29a80000,0x29a8ac00,
0xab640000,0x261f29a8,0x261fac00,0xab6429a8,0xac000000,0x2c000000,0xac000000,0x2c000000,0xab640000,0x261fa9a8,0x261f2c00,0xab64a9a8,
0xa9a80000,0xa9a8ac00,0x29a80000,0x29a82c00,0xa61f0000,0xab64a9a8,0xab64ac00,0xa61fa9a8,0,0,0,0,
0xa61f0000,0xab64a9a8,0xab64ac00,0xa61fa9a8,0xa9a80000,0xa9a8ac00,0x29a80000,0x29a82c00,0xab640000,0x261fa9a8,0x261f2c00,0xab64a9a8,
0xac000000,0x2c000000,0xac000000,0x2c000000,0xab640000,0x261f29a8,0x261fac00,0xab6429a8,0xa9a80000,0xa9a82c00,0x29a80000,0x29a8ac00,
0xa61f0000,0xab6429a8,0xab642c00,0xa61f29a8,0x2c002c00,0x2c002c00,0x2c002c00,0x2c002c00,0x2b642c00,0x261f29a8,0xa61f0000,0xab64a9a8,
0x29a82c00,0xa9a80000,0xa9a8ac00,0x29a80000,0x261f2c00,0xab64a9a8,0x2b640000,0xa61f29a8,0x2c00,0xac00,0x2c00,0xac00,
0xa61f2c00,0x2b64a9a8,0xab640000,0x261f29a8,0xa9a82c00,0x29a80000,0x29a8ac00,0xa9a80000,0xab642c00,0xa61f29a8,0x261f0000,0x2b64a9a8,
0,0,0,0,0x261f0000,0x2b64a9a8,0x2b64ac00,0x261fa9a8,0x29a80000,0x29a8ac00,0xa9a80000,0xa9a82c00,
0x2b640000,0xa61fa9a8,0xa61f2c00,0x2b64a9a8,0x2c000000,0xac000000,0x2c000000,0xac000000,0x2b640000,0xa61f29a8,0xa61fac00,0x2b6429a8,
0x29a80000,0x29a82c00,0xa9a80000,0xa9a8ac00,0x261f0000,0x2b6429a8,0x2b642c00,0x261f29a8,0xac002c00,0xac002c00,0xac002c00,0xac002c00,
0xab642c00,0xa61f29a8,0x261f0000,0x2b64a9a8,0xa9a82c00,0x29a80000,0x29a8ac00,0xa9a80000,0xa61f2c00,0x2b64a9a8,0xab640000,0x261f29a8,
0x2c00,0xac00,0x2c00,0xac00,0x261f2c00,0xab64a9a8,0x2b640000,0xa61f29a8,0x29a82c00,0xa9a80000,0xa9a8ac00,0x29a80000,
0x2b642c00,0x261f29a8,0xa61f0000,0xab64a9a8,0x2c002c00,0x2c002c00,0x2c002c00,0x2c002c00,0xab64ac00,0xa61fa9a8,0x261f0000,0x2b6429a8,
0x29a82c00,0xa9a80000,0xa9a8ac00,0x29a80000,0xa61fac00,0x2b6429a8,0xab640000,0x261fa9a8,0x2c00,0xac00,0x2c00,0xac00,
0x261fac00,0xab6429a8,0x2b640000,0xa61fa9a8,0xa9a82c00,0x29a80000,0x29a8ac00,0xa9a80000,0x2b64ac00,0x261fa9a8,0xa61f0000,0xab6429a8,
0,0,0,0,0xa61f0000,0xab64a9a8,0xab64ac00,0xa61fa9a8,0x29a80000,0x29a82c00,0xa9a80000,0xa9a8ac00,
0xab640000,0x261fa9a8,0x261f2c00,0xab64a9a8,0x2c000000,0xac000000,0x2c000000,0xac000000,0xab640000,0x261f29a8,0x261fac00,0xab6429a8,
0x29a80000,0x29a8ac00,0xa9a80000,0xa9a82c00,0xa61f0000,0xab6429a8,0xab642c00,0xa61f29a8,0xac002c00,0xac002c00,0xac002c00,0xac002c00,
0x2b64ac00,0x261fa9a8,0xa61f0000,0xab6429a8,0xa9a82c00,0x29a80000,0x29a8ac00,0xa9a80000,0x261fac00,0xab6429a8,0x2b640000,0xa61fa9a8,
0x2c00,0xac00,0x2c00,0xac00,0xa61fac00,0x2b6429a8,0xab640000,0x261fa9a8,0x29a82c00,0xa9a80000,0xa9a8ac00,0x29a80000,
0xab64ac00,0xa61fa9a8,0x261f0000,0x2b6429a8,0,0,0,0,0x261f0000,0x2b64a9a8,0x2b64ac00,0x261fa9a8,
0xa9a80000,0xa9a82c00,0x29a80000,0x29a8ac00,0x2b640000,0xa61fa9a8,0xa61f2c00,0x2b64a9a8,0xac000000,0x2c000000,0xac000000,0x2c000000,
0x2b640000,0xa61f29a8,0xa61fac00,0x2b6429a8,0xa9a80000,0xa9a8ac00,0x29a80000,0x29a82c00,0x261f0000,0x2b6429a8,0x2b642c00,0x261f29a8,
0,0,0,0,0x261f0000,0x2b6429a8,0x2b642c00,0x261f29a8,0xa9a80000,0xa9a8ac00,0x29a80000,0x29a82c00,
0x2b640000,0xa61f29a8,0xa61fac00,0x2b6429a8,0xac000000,0x2c000000,0xac000000,0x2c000000,0x2b640000,0xa61fa9a8,0xa61f2c00,0x2b64a9a8,
0xa9a80000,0xa9a82c00,0x29a80000,0x29a8ac00,0x261f0000,0x2b64a9a8,0x2b64ac00,0x261fa9a8,0x2c002c00,0x2c002c00,0x2c002c00,0x2c002c00,
0xab64ac00,0xa61fa9a8,0x261f0000,0x2b6429a8,0x29a82c00,0xa9a80000,0xa9a8ac00,0x29a80000,0xa61fac00,0x2b6429a8,0xab640000,0x261fa9a8,
0x2c00,0xac00,0x2c00,0xac00,0x261fac00,0xab6429a8,0x2b640000,0xa61fa9a8,0xa9a82c00,0x29a80000,0x29a8ac00,0xa9a80000,
0x2b64ac00,0x261fa9a8,0xa61f0000,0xab6429a8,0,0,0,0,0xa61f0000,0xab6429a8,0xab642c00,0xa61f29a8,
0x29a80000,0x29a8ac00,0xa9a80000,0xa9a82c00,0xab640000,0x261f29a8,0x261fac00,0xab6429a8,0x2c000000,0xac000000,0x2c000000,0xac000000,
0xab640000,0x261fa9a8,0x261f2c00,0xab64a9a8,0x29a80000,0x29a82c00,0xa9a80000,0xa9a8ac00,0xa61f0000,0xab64a9a8,0xab64ac00,0xa61fa9a8,
0xac002c00,0xac002c00,0xac002c00,0xac002c00,0x2b64ac00,0x261fa9a8,0xa61f0000,0xab6429a8,0xa9a82c00,0x29a80000,0x29a8ac00,0xa9a80000,
0x261fac00,0xab6429a8,0x2b640000,0xa61fa9a8,0x2c00,0xac00,0x2c00,0xac00,0xa61fac00,0x2b6429a8,0xab640000,0x261fa9a8,
0x29a82c00,0xa9a80000,0xa9a8ac00,0x29a80000,0xab64ac00,0xa61fa9a8,0x261f0000,0x2b6429a8,0x2bd92c00,0x2aa72b64,0x287229a8,0x223e261f,
0x2aa72c00,0xa23e261f,0xabd9a9a8,0xa872ab64,0x28722c00,0xabd9a61f,0x223ea9a8,0x2aa72b64,0x223e2c00,0xa872ab64,0x2aa729a8,0xabd9a61f,
0xa23e2c00,0x2872ab64,0xaaa729a8,0x2bd9a61f,0xa8722c00,0x2bd9a61f,0xa23ea9a8,0xaaa72b64,0xaaa72c00,0x223e261f,0x2bd9a9a8,0x2872ab64,
0xabd92c00,0xaaa72b64,0xa87229a8,0xa23e261f,0x223e0000,0x2872261f,0x2aa729a8,0x2bd92b64,0x28720000,0x2bd92b64,0x223e29a8,0xaaa7a61f,
0x2aa70000,0x223e2b64,0xabd9a9a8,0x2872a61f,0x2bd90000,0xaaa7261f,0x2872a9a8,0xa23e2b64,0x2bd90000,0xaaa7a61f,0x287229a8,0xa23eab64,
0x2aa70000,0x223eab64,0xabd929a8,0x2872261f,0x28720000,0x2bd9ab64,0x223ea9a8,0xaaa7261f,0x223e0000,0x2872a61f,0x2aa7a9a8,0x2bd9ab64,
0xabd92c00,0xaaa72b64,0xa87229a8,0xa23e261f,0xaaa72c00,0x223e261f,0x2bd9a9a8,0x2872ab64,0xa8722c00,0x2bd9a61f,0xa23ea9a8,0xaaa72b64,
0xa23e2c00,0x2872ab64,0xaaa729a8,0x2bd9a61f,0x223e2c00,0xa872ab64,0x2aa729a8,0xabd9a61f,0x28722c00,0xabd9a61f,0x223ea9a8,0x2aa72b64,
0x2aa72c00,0xa23e261f,0xabd9a9a8,0xa872ab64,0x2bd92c00,0x2aa72b64,0x287229a8,0x223e261f,0xa23e0000,0xa872261f,0xaaa729a8,0xabd92b64,
0xa8720000,0xabd92b64,0xa23e29a8,0x2aa7a61f,0xaaa70000,0xa23e2b64,0x2bd9a9a8,0xa872a61f,0xabd90000,0x2aa7261f,0xa872a9a8,0x223e2b64,
0xabd90000,0x2aa7a61f,0xa87229a8,0x223eab64,0xaaa70000,0xa23eab64,0x2bd929a8,0xa872261f,0xa8720000,0xabd9ab64,0xa23ea9a8,0x2aa7261f,
0xa23e0000,0xa872a61f,0xaaa7a9a8,0xabd9ab64,0xa23e0000,0xa872a61f,0xaaa7a9a8,0xabd9ab64,0xa8720000,0xabd9ab64,0xa23ea9a8,0x2aa7261f,
0xaaa70000,0xa23eab64,0x2bd929a8,0xa872261f,0xabd90000,0x2aa7a61f,0xa87229a8,0x223eab64,0xabd90000,0x2aa7261f,0xa872a9a8,0x223e2b64,
0xaaa70000,0xa23e2b64,0x2bd9a9a8,0xa872a61f,0xa8720000,0xabd92b64,0xa23e29a8,0x2aa7a61f,0xa23e0000,0xa872261f,0xaaa729a8,0xabd92b64,
0x2bd92c00,0x2aa72b64,0x287229a8,0x223e261f,0x2aa72c00,0xa23e261f,0xabd9a9a8,0xa872ab64,0x28722c00,0xabd9a61f,0x223ea9a8,0x2aa72b64,
0x223e2c00,0xa872ab64,0x2aa729a8,0xabd9a61f,0xa23e2c00,0x2872ab64,0xaaa729a8,0x2bd9a61f,0xa8722c00,0x2bd9a61f,0xa23ea9a8,0xaaa72b64,
0xaaa72c00,0x223e261f,0x2bd9a9a8,0x2872ab64,0xabd92c00,0xaaa72b64,0xa87229a8,0xa23e261f,0x223e0000,0x2872a61f,0x2aa7a9a8,0x2bd9ab64,
0x28720000,0x2bd9ab64,0x223ea9a8,0xaaa7261f,0x2aa70000,0x223eab64,0xabd929a8,0x2872261f,0x2bd90000,0xaaa7a61f,0x287229a8,0xa23eab64,
0x2bd90000,0xaaa7261f,0x2872a9a8,0xa23e2b64,0x2aa70000,0x223e2b64,0xabd9a9a8,0x2872a61f,0x28720000,0x2bd92b64,0x223e29a8,0xaaa7a61f,
0x223e0000,0x2872261f,0x2aa729a8,0x2bd92b64,0xabd92c00,0xaaa72b64,0xa87229a8,0xa23e261f,0xaaa72c00,0x223e261f,0x2bd9a9a8,0x2872ab64,
0xa8722c00,0x2bd9a61f,0xa23ea9a8,0xaaa72b64,0xa23e2c00,0x2872ab64,0xaaa729a8,0x2bd9a61f,0x223e2c00,0xa872ab64,0x2aa729a8,0xabd9a61f,
0x28722c00,0xabd9a61f,0x223ea9a8,0x2aa72b64,0x2aa72c00,0xa23e261f,0xabd9a9a8,0xa872ab64,0x2bd92c00,0x2aa72b64,0x287229a8,0x223e261f,
0xa23e0000,0xa872a61f,0xaaa7a9a8,0xabd9ab64,0x28720000,0x2bd92b64,0x223e29a8,0xaaa7a61f,0xaaa70000,0xa23eab64,0x2bd929a8,0xa872261f,
0x2bd90000,0xaaa7261f,0x2872a9a8,0xa23e2b64,0xabd90000,0x2aa7261f,0xa872a9a8,0x223e2b64,0x2aa70000,0x223eab64,0xabd929a8,0x2872261f,
0xa8720000,0xabd92b64,0xa23e29a8,0x2aa7a61f,0x223e0000,0x2872a61f,0x2aa7a9a8,0x2bd9ab64,0x2bd92c00,0x2aa72b64,0x287229a8,0x223e261f,
0xaaa7ac00,0x223ea61f,0x2bd929a8,0x28722b64,0x28722c00,0xabd9a61f,0x223ea9a8,0x2aa72b64,0xa23eac00,0x28722b64,0xaaa7a9a8,0x2bd9261f,
0xa23e2c00,0x2872ab64,0xaaa729a8,0x2bd9a61f,0x2872ac00,0xabd9261f,0x223e29a8,0x2aa7ab64,0xaaa72c00,0x223e261f,0x2bd9a9a8,0x2872ab64,
0x2bd9ac00,0x2aa7ab64,0x2872a9a8,0x223ea61f,0x223e0000,0x2872a61f,0x2aa7a9a8,0x2bd9ab64,0xa8720000,0xabd92b64,0xa23e29a8,0x2aa7a61f,
0x2aa70000,0x223eab64,0xabd929a8,0x2872261f,0xabd90000,0x2aa7261f,0xa872a9a8,0x223e2b64,0x2bd90000,0xaaa7261f,0x2872a9a8,0xa23e2b64,
0xaaa70000,0xa23eab64,0x2bd929a8,0xa872261f,0x28720000,0x2bd92b64,0x223e29a8,0xaaa7a61f,0xa23e0000,0xa872a61f,0xaaa7a9a8,0xabd9ab64,
0xabd92c00,0xaaa72b64,0xa87229a8,0xa23e261f,0x2aa7ac00,0xa23ea61f,0xabd929a8,0xa8722b64,0xa8722c00,0x2bd9a61f,0xa23ea9a8,0xaaa72b64,
0x223eac00,0xa8722b64,0x2aa7a9a8,0xabd9261f,0x223e2c00,0xa872ab64,0x2aa729a8,0xabd9a61f,0xa872ac00,0x2bd9261f,0xa23e29a8,0xaaa7ab64,
0x2aa72c00,0xa23e261f,0xabd9a9a8,0xa872ab64,0xabd9ac00,0xaaa7ab64,0xa872a9a8,0xa23ea61f,0xabd9ac00,0xaaa7ab64,0xa872a9a8,0xa23ea61f,
0x2aa72c00,0xa23e261f,0xabd9a9a8,0xa872ab64,0xa872ac00,0x2bd9261f,0xa23e29a8,0xaaa7ab64,0x223e2c00,0xa872ab64,0x2aa729a8,0xabd9a61f,
0x223eac00,0xa8722b64,0x2aa7a9a8,0xabd9261f,0xa8722c00,0x2bd9a61f,0xa23ea9a8,0xaaa72b64,0x2aa7ac00,0xa23ea61f,0xabd929a8,0xa8722b64,
0xabd92c00,0xaaa72b64,0xa87229a8,0xa23e261f,0xa23e0000,0xa872a61f,0xaaa7a9a8,0xabd9ab64,0x28720000,0x2bd92b64,0x223e29a8,0xaaa7a61f,
0xaaa70000,0xa23eab64,0x2bd929a8,0xa872261f,0x2bd90000,0xaaa7261f,0x2872a9a8,0xa23e2b64,0xabd90000,0x2aa7261f,0xa872a9a8,0x223e2b64,
0x2aa70000,0x223eab64,0xabd929a8,0x2872261f,0xa8720000,0xabd92b64,0xa23e29a8,0x2aa7a61f,0x223e0000,0x2872a61f,0x2aa7a9a8,0x2bd9ab64,
0x2bd9ac00,0x2aa7ab64,0x2872a9a8,0x223ea61f,0xaaa72c00,0x223e261f,0x2bd9a9a8,0x2872ab64,0x2872ac00,0xabd9261f,0x223e29a8,0x2aa7ab64,
0xa23e2c00,0x2872ab64,0xaaa729a8,0x2bd9a61f,0xa23eac00,0x28722b64,0xaaa7a9a8,0x2bd9261f,0x28722c00,0xabd9a61f,0x223ea9a8,0x2aa72b64,
0xaaa7ac00,0x223ea61f,0x2bd929a8,0x28722b64,0x2bd92c00,0x2aa72b64,0x287229a8,0x223e261f,0x223e0000,0x2872a61f,0x2aa7a9a8,0x2bd9ab64,
0xa8720000,0xabd92b64,0xa23e29a8,0x2aa7a61f,0x2aa70000,0x223eab64,0xabd929a8,0x2872261f,0xabd90000,0x2aa7261f,0xa872a9a8,0x223e2b64,
0x2bd90000,0xaaa7261f,0x2872a9a8,0xa23e2b64,0xaaa70000,0xa23eab64,0x2bd929a8,0xa872261f,0x28720000,0x2bd92b64,0x223e29a8,0xaaa7a61f,
0xa23e0000,0xa872a61f,0xaaa7a9a8,0xabd9ab64,0x27fe2800,0x96480000,0x273b2764,0xa2d7a21f,0x27ea27f6,0x9cb29a46,0x26dd270e,0xa41da38b,
0x27c327d9,0x9fc69e3e,0x266d26a7,0xa4c4a472,0x278827a8,0xa164a0a5,0x25ed262f,0xa55fa513,0x27c32800,0x9fc60000,0xa4c4a21f,0xa66da764,
0x25ed270e,0xa55fa38b,0xa73ba62f,0xa2d7a513,0x21642472,0xa788a6a7,0xa7fea7d9,0x16489e3e,0x9cb21a46,0xa7eaa7f6,0xa6dda7a8,0x241d20a5,
0x273b2800,0xa2d70000,0xa55fa764,0x25ed221f,0x1fc62513,0xa7c3a62f,0x1cb2a0a5,0x27ea27a8,0xa4c49e3e,0xa66da7d9,0x26dd2472,0x241d26a7,
0xa7fea70e,0x9648a38b,0x278827f6,0xa1641a46,0x266d2800,0xa4c40000,0x26dd221f,0x241d2764,0xa16420a5,0xa788a7a8,0x25ed27f6,0xa55f9a46,
0xa7fea6a7,0x1648a472,0xa2d71e3e,0xa73ba7d9,0x9fc6a62f,0x27c32513,0xa7eaa70e,0x1cb2a38b,0x255f2800,0xa5ed0000,0x21642764,0xa788a21f,
0xa66d9a46,0xa4c4a7f6,0xa7c3a38b,0x9fc6a70e,0xa41da7d9,0x26dd1e3e,0x9cb2a6a7,0x27ea2472,0x273b20a5,0x22d727a8,0x27fe2513,0x1648262f,
0x241d2800,0xa6dd0000,0xa7eaa21f,0x9cb2a764,0xa7fea38b,0x9648a70e,0x2164a513,0x2788262f,0x22d7a472,0x273b26a7,0x255f27d9,0xa5ed1e3e,
0x24c427f6,0xa66d1a46,0xa7c3a0a5,0x9fc6a7a8,0x21642800,0xa7880000,0x1648a764,0x27fe221f,0xa6dda62f,0x241da513,0x24c427a8,0xa66d20a5,
0x27ea1e3e,0x1cb227d9,0xa7c3a472,0x1fc6a6a7,0xa55f238b,0xa5eda70e,0x273b9a46,0x22d727f6,0x1cb22800,0xa7ea0000,0x27c3221f,0x9fc62764,
0xa2d7a7a8,0x273ba0a5,0xa7fe9a46,0x9648a7f6,0x255f26a7,0xa5ed2472,0x27889e3e,0x216427d9,0xa6dda513,0x241da62f,0xa66d238b,0xa4c4a70e,
0x96482800,0xa7fe0000,0xa2d72764,0xa73ba21f,0x1cb2a7f6,0x27ea1a46,0x241da70e,0x26dd238b,0x9fc627d9,0xa7c39e3e,0xa4c426a7,0xa66da472,
0x2164a7a8,0x278820a5,0x255fa62f,0x25ed2513,0x9fc62800,0xa7c30000,0xa66da21f,0x24c4a764,0x255fa70e,0x25ed238b,0x22d7262f,0xa73b2513,
0xa7882472,0xa164a6a7,0x1648a7d9,0x27fe9e3e,0x27ea9a46,0x9cb227f6,0xa41d27a8,0xa6dda0a5,0xa2d72800,0xa73b0000,0x25eda764,0x255f221f,
0x27c3a513,0x1fc6262f,0xa7ea20a5,0x1cb2a7a8,0xa66d9e3e,0x24c4a7d9,0x241d2472,0xa6dd26a7,0x1648270e,0xa7fe238b,0x2164a7f6,0x27889a46,
0xa4c42800,0xa66d0000,0x241d221f,0xa6dd2764,0x2788a0a5,0xa16427a8,0x255fa7f6,0x25ed1a46,0x1648a6a7,0x27fea472,0xa73b1e3e,0x22d7a7d9,
0xa7c3262f,0x9fc6a513,0x9cb2270e,0xa7ea238b,0xa5ed2800,0xa55f0000,0xa7882764,0xa164a21f,0x24c41a46,0xa66d27f6,0x1fc6238b,0xa7c3270e,
0x26dda7d9,0x241d1e3e,0x27eaa6a7,0x1cb22472,0xa2d7a0a5,0x273ba7a8,0x9648a513,0x27fea62f,0xa6dd2800,0xa41d0000,0x9cb2a21f,0x27eaa764,
0x1648238b,0xa7fe270e,0xa7882513,0x2164a62f,0x273ba472,0xa2d726a7,0xa5ed27d9,0xa55f1e3e,0x266da7f6,0x24c49a46,0x1fc620a5,0xa7c327a8,
0xa7882800,0xa1640000,0x27fea764,0x9648221f,0xa41d262f,0xa6dd2513,0x266da7a8,0x24c4a0a5,0x1cb21e3e,0xa7ea27d9,0x1fc6a472,0x27c3a6a7,
0x25eda38b,0xa55f270e,0xa2d71a46,0x273ba7f6,0xa7ea2800,0x9cb20000,0x9fc6221f,0xa7c32764,0xa73b27a8,0xa2d720a5,0x16481a46,0xa7fe27f6,
0xa5ed26a7,0xa55f2472,0x21649e3e,0xa78827d9,0xa41d2513,0xa6dd262f,0x24c4a38b,0xa66d270e,0xa7fe2800,0x16480000,0xa73b2764,0x22d7a21f,
0xa7ea27f6,0x1cb29a46,0xa6dd270e,0x241da38b,0xa7c327d9,0x1fc69e3e,0xa66d26a7,0x24c4a472,0xa78827a8,0x2164a0a5,0xa5ed262f,0x255fa513,
0xa7c32800,0x1fc60000,0x24c4a21f,0x266da764,0xa5ed270e,0x255fa38b,0x273ba62f,0x22d7a513,0xa1642472,0x2788a6a7,0x27fea7d9,0x96489e3e,
0x1cb21a46,0x27eaa7f6,0x26dda7a8,0xa41d20a5,0xa73b2800,0x22d70000,0x255fa764,0xa5ed221f,0x9fc62513,0x27c3a62f,0x9cb2a0a5,0xa7ea27a8,
0x24c49e3e,0x266da7d9,0xa6dd2472,0xa41d26a7,0x27fea70e,0x1648a38b,0xa78827f6,0x21641a46,0xa66d2800,0x24c40000,0xa6dd221f,0xa41d2764,
0x216420a5,0x2788a7a8,0xa5ed27f6,0x255f9a46,0x27fea6a7,0x9648a472,0x22d71e3e,0x273ba7d9,0x1fc6a62f,0xa7c32513,0x27eaa70e,0x9cb2a38b,
0xa55f2800,0x25ed0000,0xa1642764,0x2788a21f,0x266d9a46,0x24c4a7f6,0x27c3a38b,0x1fc6a70e,0x241da7d9,0xa6dd1e3e,0x1cb2a6a7,0xa7ea2472,
0xa73b20a5,0xa2d727a8,0xa7fe2513,0x9648262f,0xa41d2800,0x26dd0000,0x27eaa21f,0x1cb2a764,0x27fea38b,0x1648a70e,0xa164a513,0xa788262f,
0xa2d7a472,0xa73b26a7,0xa55f27d9,0x25ed1e3e,0xa4c427f6,0x266d1a46,0x27c3a0a5,0x1fc6a7a8,0xa1642800,0x27880000,0x9648a764,0xa7fe221f,
0x26dda62f,0xa41da513,0xa4c427a8,0x266d20a5,0xa7ea1e3e,0x9cb227d9,0x27c3a472,0x9fc6a6a7,0x255f238b,0x25eda70e,0xa73b9a46,0xa2d727f6,
0x9cb22800,0x27ea0000,0xa7c3221f,0x1fc62764,0x22d7a7a8,0xa73ba0a5,0x27fe9a46,0x1648a7f6,0xa55f26a7,0x25ed2472,0xa7889e3e,0xa16427d9,
0x26dda513,0xa41da62f,0x266d238b,0x24c4a70e,0x16482800,0x27fe0000,0x22d72764,0x273ba21f,0x9cb2a7f6,0xa7ea1a46,0xa41da70e,0xa6dd238b,
0x1fc627d9,0x27c39e3e,0x24c426a7,0x266da472,0xa164a7a8,0xa78820a5,0xa55fa62f,0xa5ed2513,0x1fc62800,0x27c30000,0x266da21f,0xa4c4a764,
0xa55fa70e,0xa5ed238b,0xa2d7262f,0x273b2513,0x27882472,0x2164a6a7,0x9648a7d9,0xa7fe9e3e,0xa7ea9a46,0x1cb227f6,0x241d27a8,0x26dda0a5,
0x22d72800,0x273b0000,0xa5eda764,0xa55f221f,0xa7c3a513,0x9fc6262f,0x27ea20a5,0x9cb2a7a8,0x266d9e3e,0xa4c4a7d9,0xa41d2472,0x26dd26a7,
0x9648270e,0x27fe238b,0xa164a7f6,0xa7889a46,0x24c42800,0x266d0000,0xa41d221f,0x26dd2764,0xa788a0a5,0x216427a8,0xa55fa7f6,0xa5ed1a46,
0x9648a6a7,0xa7fea472,0x273b1e3e,0xa2d7a7d9,0x27c3262f,0x1fc6a513,0x1cb2270e,0x27ea238b,0x25ed2800,0x255f0000,0x27882764,0x2164a21f,
0xa4c41a46,0x266d27f6,0x9fc6238b,0x27c3270e,0xa6dda7d9,0xa41d1e3e,0xa7eaa6a7,0x9cb22472,0x22d7a0a5,0xa73ba7a8,0x1648a513,0xa7fea62f,
0x26dd2800,0x241d0000,0x1cb2a21f,0xa7eaa764,0x9648238b,0x27fe270e,0x27882513,0xa164a62f,0xa73ba472,0x22d726a7,0x25ed27d9,0x255f1e3e,
0xa66da7f6,0xa4c49a46,0x9fc620a5,0x27c327a8,0x27882800,0x21640000,0xa7fea764,0x1648221f,0x241d262f,0x26dd2513,0xa66da7a8,0xa4c4a0a5,
0x9cb21e3e,0x27ea27d9,0x9fc6a472,0xa7c3a6a7,0xa5eda38b,0x255f270e,0x22d71a46,0xa73ba7f6,0x27ea2800,0x1cb20000,0x1fc6221f,0x27c32764,
0x273b27a8,0x22d720a5,0x96481a46,0x27fe27f6,0x25ed26a7,0x255f2472,0xa1649e3e,0x278827d9,0x241d2513,0x26dd262f,0xa4c4a38b,0x266d270e,
0x255f25a8,0xa5eda5a8,0x2164221f,0xa788a764,0x24c42513,0xa66da62f,0x1fc620a5,0xa7c3a7a8,0x241d2472,0xa6dda6a7,0x1cb21e3e,0xa7eaa7d9,
0x22d7238b,0xa73ba70e,0x16481a46,0xa7fea7f6,0xa41da5a8,0x26dd25a8,0x27ea2764,0x1cb2221f,0x9648a0a5,0x27fe27a8,0x278827f6,0xa1649a46,
0x22d71e3e,0x273b27d9,0x255f26a7,0xa5eda472,0x266d2513,0x24c4262f,0x1fc6238b,0xa7c3a70e,0x216425a8,0xa788a5a8,0x1648a21f,0x27fe2764,
0xa41d9a46,0xa6dda7f6,0x266d238b,0x24c4270e,0xa7eaa6a7,0x9cb2a472,0x27c327d9,0x9fc61e3e,0xa5eda7a8,0x255f20a5,0x22d7262f,0xa73ba513,
0x9cb2a5a8,0x27ea25a8,0xa7c3a764,0x1fc6a21f,0x273b238b,0x22d7270e,0x9648a513,0x27fe262f,0x255f27d9,0xa5ed9e3e,0x27882472,0x216426a7,
0xa41d1a46,0xa6dda7f6,0x24c427a8,0xa66da0a5,0x964825a8,0xa7fea5a8,0xa2d7221f,0xa73ba764,0xa7eaa62f,0x1cb2a513,0xa6dda7a8,0x241da0a5,
0x1fc6a472,0x27c326a7,0x24c49e3e,0x266d27d9,0x2788270e,0xa164238b,0x25ed27f6,0xa55f1a46,0x1fc6a5a8,0x27c325a8,0x266d2764,0xa4c4221f,
0x25ed27a8,0xa55f20a5,0xa73b9a46,0xa2d7a7f6,0xa7889e3e,0xa164a7d9,0x1648a6a7,0x27fe2472,0x1cb2a62f,0x27ea2513,0x26dd270e,0xa41d238b,
0xa2d725a8,0xa73ba5a8,0x25eda21f,0x255f2764,0x9fc6a7f6,0x27c31a46,0x9cb2270e,0xa7eaa38b,0x266d26a7,0xa4c42472,0xa41da7d9,0x26dd9e3e,
0xa7fea0a5,0x9648a7a8,0x27882513,0xa164262f,0x24c4a5a8,0x266d25a8,0xa41da764,0x26dda21f,0xa164270e,0xa788a38b,0x25ed262f,0xa55f2513,
0x1648a7d9,0x27fe1e3e,0xa73ba472,0x22d7a6a7,0x1fc627f6,0xa7c31a46,0x27ea20a5,0x9cb227a8,0xa5ed25a8,0xa55fa5a8,0xa788221f,0xa164a764,
0x266da513,0x24c4262f,0x27c3a0a5,0x1fc627a8,0xa6dd2472,0xa41da6a7,0xa7ea1e3e,0x9cb2a7d9,0x273ba38b,0x22d7270e,0x27fe9a46,0x164827f6,
0x26dda5a8,0x241d25a8,0x1cb22764,0xa7ea221f,0xa7fe20a5,0x9648a7a8,0x2164a7f6,0x27881a46,0x273b1e3e,0xa2d727d9,0xa5ed26a7,0xa55fa472,
0xa4c4a513,0x266da62f,0x27c3a38b,0x1fc6270e,0xa78825a8,0xa164a5a8,0x27fea21f,0x96482764,0x26dd1a46,0xa41d27f6,0xa4c4a38b,0x266da70e,
0x9cb2a6a7,0x27eaa472,0x9fc627d9,0xa7c31e3e,0xa55f27a8,0xa5eda0a5,0x273ba62f,0x22d72513,0x27eaa5a8,0x1cb225a8,0x1fc6a764,0x27c3a21f,
0xa2d7a38b,0x273ba70e,0xa7fe2513,0x9648a62f,0xa5ed27d9,0xa55f9e3e,0x21642472,0xa78826a7,0x26dd9a46,0xa41d27f6,0x266da7a8,0x24c420a5,
0xa7fe25a8,0x1648a5a8,0xa73b221f,0x22d7a764,0x9cb2262f,0xa7ea2513,0xa41d27a8,0xa6dd20a5,0x27c3a472,0x9fc626a7,0x266d9e3e,0xa4c427d9,
0x2164a70e,0x2788a38b,0x255fa7f6,0x25ed9a46,0x27c3a5a8,0x9fc625a8,0xa4c42764,0xa66d221f,0x255fa7a8,0x25eda0a5,0x22d71a46,0xa73b27f6,
0xa1649e3e,0x2788a7d9,0x27fea6a7,0x96482472,0xa7ea262f,0x1cb2a513,0x241da70e,0x26dda38b,0xa73b25a8,0x22d7a5a8,0x255fa21f,0xa5ed2764,
0xa7c327f6,0x9fc69a46,0x27eaa70e,0x9cb2238b,0xa4c426a7,0xa66d2472,0x26dda7d9,0x241d9e3e,0x164820a5,0xa7fe27a8,0x2164a513,0x2788a62f,
0x266da5a8,0xa4c425a8,0x26dda764,0x241da21f,0x2788a70e,0xa164238b,0x255fa62f,0x25eda513,0x27fea7d9,0x96481e3e,0x22d7a472,0x273ba6a7,
0x27c3a7f6,0x1fc69a46,0x1cb2a0a5,0x27eaa7a8,0xa55f25a8,0x25eda5a8,0xa164221f,0x2788a764,0xa4c42513,0x266da62f,0x9fc620a5,0x27c3a7a8,
0xa41d2472,0x26dda6a7,0x9cb21e3e,0x27eaa7d9,0xa2d7238b,0x273ba70e,0x96481a46,0x27fea7f6,0x241da5a8,0xa6dd25a8,0xa7ea2764,0x9cb2221f,
0x1648a0a5,0xa7fe27a8,0xa78827f6,0x21649a46,0xa2d71e3e,0xa73b27d9,0xa55f26a7,0x25eda472,0xa66d2513,0xa4c4262f,0x9fc6238b,0x27c3a70e,
0xa16425a8,0x2788a5a8,0x9648a21f,0xa7fe2764,0x241d9a46,0x26dda7f6,0xa66d238b,0xa4c4270e,0x27eaa6a7,0x1cb2a472,0xa7c327d9,0x1fc61e3e,
0x25eda7a8,0xa55f20a5,0xa2d7262f,0x273ba513,0x1cb2a5a8,0xa7ea25a8,0x27c3a764,0x9fc6a21f,0xa73b238b,0xa2d7270e,0x1648a513,0xa7fe262f,
0xa55f27d9,0x25ed9e3e,0xa7882472,0xa16426a7,0x241d1a46,0x26dda7f6,0xa4c427a8,0x266da0a5,0x164825a8,0x27fea5a8,0x22d7221f,0x273ba764,
0x27eaa62f,0x9cb2a513,0x26dda7a8,0xa41da0a5,0x9fc6a472,0xa7c326a7,0xa4c49e3e,0xa66d27d9,0xa788270e,0x2164238b,0xa5ed27f6,0x255f1a46,
0x9fc6a5a8,0xa7c325a8,0xa66d2764,0x24c4221f,0xa5ed27a8,0x255f20a5,0x273b9a46,0x22d7a7f6,0x27889e3e,0x2164a7d9,0x9648a6a7,0xa7fe2472,
0x9cb2a62f,0xa7ea2513,0xa6dd270e,0x241d238b,0x22d725a8,0x273ba5a8,0xa5eda21f,0xa55f2764,0x1fc6a7f6,0xa7c31a46,0x1cb2270e,0x27eaa38b,
0xa66d26a7,0x24c42472,0x241da7d9,0xa6dd9e3e,0x27fea0a5,0x1648a7a8,0xa7882513,0x2164262f,0xa4c4a5a8,0xa66d25a8,0x241da764,0xa6dda21f,
0x2164270e,0x2788a38b,0xa5ed262f,0x255f2513,0x9648a7d9,0xa7fe1e3e,0x273ba472,0xa2d7a6a7,0x9fc627f6,0x27c31a46,0xa7ea20a5,0x1cb227a8,
0x25ed25a8,0x255fa5a8,0x2788221f,0x2164a764,0xa66da513,0xa4c4262f,0xa7c3a0a5,0x9fc627a8,0x26dd2472,0x241da6a7,0x27ea1e3e,0x1cb2a7d9,
0xa73ba38b,0xa2d7270e,0xa7fe9a46,0x964827f6,0xa6dda5a8,0xa41d25a8,0x9cb22764,0x27ea221f,0x27fe20a5,0x1648a7a8,0xa164a7f6,0xa7881a46,
0xa73b1e3e,0x22d727d9,0x25ed26a7,0x255fa472,0x24c4a513,0xa66da62f,0xa7c3a38b,0x9fc6270e,0x278825a8,0x2164a5a8,0xa7fea21f,0x16482764,
0xa6dd1a46,0x241d27f6,0x24c4a38b,0xa66da70e,0x1cb2a6a7,0xa7eaa472,0x1fc627d9,0x27c31e3e,0x255f27a8,0x25eda0a5,0xa73ba62f,0xa2d72513,
0xa7eaa5a8,0x9cb225a8,0x9fc6a764,0xa7c3a21f,0x22d7a38b,0xa73ba70e,0x27fe2513,0x1648a62f,0x25ed27d9,0x255f9e3e,0xa1642472,0x278826a7,
0xa6dd9a46,0x241d27f6,0xa66da7a8,0xa4c420a5,0x27fe25a8,0x9648a5a8,0x273b221f,0xa2d7a764,0x1cb2262f,0x27ea2513,0x241d27a8,0x26dd20a5,
0xa7c3a472,0x1fc626a7,0xa66d9e3e,0x24c427d9,0xa164a70e,0xa788a38b,0xa55fa7f6,0xa5ed9a46,0xa7c3a5a8,0x1fc625a8,0x24c42764,0x266d221f,
0xa55fa7a8,0xa5eda0a5,0xa2d71a46,0x273b27f6,0x21649e3e,0xa788a7d9,0xa7fea6a7,0x16482472,0x27ea262f,0x9cb2a513,0xa41da70e,0xa6dda38b,
0x273b25a8,0xa2d7a5a8,0xa55fa21f,0x25ed2764,0x27c327f6,0x1fc69a46,0xa7eaa70e,0x1cb2238b,0x24c426a7,0x266d2472,0xa6dda7d9,0xa41d9e3e,
0x964820a5,0x27fe27a8,0xa164a513,0xa788a62f,0xa66da5a8,0x24c425a8,0xa6dda764,0xa41da21f,0xa788a70e,0x2164238b,0xa55fa62f,0xa5eda513,
0xa7fea7d9,0x16481e3e,0xa2d7a472,0xa73ba6a7,0xa7c3a7f6,0x9fc69a46,0x9cb2a0a5,0xa7eaa7a8,
};

#define PROF(slot) do {} while (0)
#define PROF3(slot) do {} while (0)
#define PROF2(slot) do {} while (0)

__device__ __forceinline__ uint32_t smem_u32(const void* p) { return (uint32_t)__cvta_generic_to_shared(p); }

__device__ __forceinline__ void mbar_init(uint32_t a, uint32_t c) {
  asm volatile("mbarrier.init.shared::cta.b64 [%0], %1;\n" ::"r"(a), "r"(c) : "memory");
}
__device__ __forceinline__ void mbar_expect_tx(uint32_t a, uint32_t bytes) {
  asm volatile("mbarrier.arrive.expect_tx.shared::cta.b64 _, [%0], %1;\n" ::"r"(a), "r"(bytes) : "memory");
}
__device__ __forceinline__ void mbar_arrive_cluster(uint32_t cluster_addr) {
  asm volatile("mbarrier.arrive.shared::cluster.b64 _, [%0];\n" ::"r"(cluster_addr) : "memory");
}
__device__ __forceinline__ void mbar_arrive_cluster_n(uint32_t cluster_addr, uint32_t n) {
  asm volatile("mbarrier.arrive.shared::cluster.b64 _, [%0], %1;\n" ::"r"(cluster_addr), "r"(n) : "memory");
}
__device__ __forceinline__ bool mbar_try(uint32_t a, uint32_t parity) {
  uint32_t ok;
  asm volatile("{\n.reg .pred p;\nmbarrier.try_wait.parity.shared::cta.b64 p, [%1], %2;\nselp.u32 %0, 1, 0, p;\n}\n"
               : "=r"(ok) : "r"(a), "r"(parity) : "memory");
  return ok;
}
__device__ __forceinline__ void mbar_wait(uint32_t a, uint32_t parity) {
  if (mbar_try(a, parity)) return;
#pragma unroll 1
  for (int n = 0; n < SPIN_LIMIT; n++)
    if (mbar_try(a, parity)) break;
}
__device__ __forceinline__ void mbar_wait_idle(uint32_t a, uint32_t parity) {
#pragma unroll 1
  for (int n = 0; n < SPIN_LIMIT; n++) {
    uint32_t ok;
    asm volatile("{\n.reg .pred p;\nmbarrier.try_wait.parity.shared::cta.b64 p, [%1], %2, %3;\nselp.u32 %0, 1, 0, p;\n}\n"
                 : "=r"(ok) : "r"(a), "r"(parity), "r"(4000) : "memory");
    if (ok) break;
  }
}
__device__ __forceinline__ bool elect_one() {
  uint32_t p;
  asm volatile("{\n.reg .pred P;\nelect.sync _|P, 0xffffffff;\nselp.u32 %0, 1, 0, P;\n}\n" : "=r"(p));
  return p;
}
__device__ __forceinline__ uint32_t mapa(uint32_t a, uint32_t rank) {
  uint32_t r;
  asm volatile("mapa.shared::cluster.u32 %0, %1, %2;\n" : "=r"(r) : "r"(a), "r"(rank));
  return r;
}
__device__ __forceinline__ void nb_sync(int id, int n) { asm volatile("bar.sync %0, %1;\n" ::"r"(id), "r"(n) : "memory"); }
__device__ __forceinline__ void nb_arrive(int id, int n) { asm volatile("bar.arrive %0, %1;\n" ::"r"(id), "r"(n) : "memory"); }
__device__ __forceinline__ void cluster_sync_all() {
  asm volatile("barrier.cluster.arrive.relaxed.aligned;\nbarrier.cluster.wait.aligned;\n" ::: "memory");
}
__device__ __forceinline__ void fence_async_smem() { asm volatile("fence.proxy.async.shared::cta;\n" ::: "memory"); }
__device__ __forceinline__ void fence_async_all() { asm volatile("fence.proxy.async.global;\n" ::: "memory"); }

__device__ __forceinline__ void tma_load_3d(uint32_t dst, const CUtensorMap* tm, uint32_t bar, int c0, int c1, int c2) {
  asm volatile(
      "cp.async.bulk.tensor.3d.shared::cluster.global.mbarrier::complete_tx::bytes [%0], [%1, {%3, %4, %5}], [%2];\n"
      ::"r"(dst), "l"(tm), "r"(bar), "r"(c0), "r"(c1), "r"(c2) : "memory");
}
__device__ __forceinline__ void tma_load_4d(uint32_t dst, const CUtensorMap* tm, uint32_t bar, int c0, int c1, int c2, int c3) {
  asm volatile(
      "cp.async.bulk.tensor.4d.shared::cluster.global.mbarrier::complete_tx::bytes [%0], [%1, {%3, %4, %5, %6}], [%2];\n"
      ::"r"(dst), "l"(tm), "r"(bar), "r"(c0), "r"(c1), "r"(c2), "r"(c3) : "memory");
}
__device__ __forceinline__ void tma_load_3d_mc(uint32_t dst, const CUtensorMap* tm, uint32_t bar, int c0, int c1, int c2) {
  asm volatile(
      "cp.async.bulk.tensor.3d.shared::cluster.global.mbarrier::complete_tx::bytes.multicast::cluster [%0], [%1, {%3, %4, %5}], [%2], %6;\n"
      ::"r"(dst), "l"(tm), "r"(bar), "r"(c0), "r"(c1), "r"(c2), "h"((uint16_t)3) : "memory");
}
__device__ __forceinline__ void tma_load_5d(uint32_t dst, const CUtensorMap* tm, uint32_t bar, int c0, int c4) {
  asm volatile(
      "cp.async.bulk.tensor.5d.shared::cluster.global.mbarrier::complete_tx::bytes [%0], [%1, {%3, %5, %5, %5, %4}], [%2];\n"
      ::"r"(dst), "l"(tm), "r"(bar), "r"(c0), "r"(c4), "r"(0) : "memory");
}
__device__ __forceinline__ void bulk_load(uint32_t dst, const void* src, uint32_t bytes, uint32_t bar) {
  asm volatile("cp.async.bulk.shared::cluster.global.mbarrier::complete_tx::bytes [%0], [%1], %2, [%3];\n"
               ::"r"(dst), "l"(src), "r"(bytes), "r"(bar) : "memory");
}
__device__ __forceinline__ void bulk_commit() { asm volatile("cp.async.bulk.commit_group;\n" ::: "memory"); }
__device__ __forceinline__ void bulk_wait0() { asm volatile("cp.async.bulk.wait_group 0;\n" ::: "memory"); }
__device__ __forceinline__ void prefetch_tmap(const CUtensorMap* tm) {
  asm volatile("prefetch.tensormap [%0];\n" ::"l"(tm) : "memory");
}

__device__ __forceinline__ void wg_fence() { asm volatile("wgmma.fence.sync.aligned;\n" ::: "memory"); }
__device__ __forceinline__ void wg_commit() { asm volatile("wgmma.commit_group.sync.aligned;\n" ::: "memory"); }
template <int N> __device__ __forceinline__ void wg_wait() {
  asm volatile("wgmma.wait_group.sync.aligned %0;\n" ::"n"(N) : "memory");
}
__device__ __forceinline__ uint64_t mkdesc(uint32_t addr, uint32_t lbo, uint32_t sbo, uint32_t swz) {
  return (uint64_t)((addr & 0x3FFFF) >> 4) | ((uint64_t)(lbo >> 4) << 16) | ((uint64_t)(sbo >> 4) << 32) |
         ((uint64_t)swz << 62);
}

#define R4(d, o) "+f"(d[o + 0]), "+f"(d[o + 1]), "+f"(d[o + 2]), "+f"(d[o + 3])
#define R8(d, o) R4(d, o), R4(d, o + 4)
#define R16(d, o) R8(d, o), R8(d, o + 8)
#define R32(d, o) R16(d, o), R16(d, o + 16)
#define R64(d, o) R32(d, o), R32(d, o + 32)

__device__ __forceinline__ void wgmma_n192(float (&d)[96], uint64_t da, uint64_t db, uint32_t acc) {
  asm volatile(
      "{\n.reg .pred p;\nsetp.ne.u32 p, %98, 0;\n"
      "wgmma.mma_async.sync.aligned.m64n192k16.f32.bf16.bf16 "
      "{%0,%1,%2,%3,%4,%5,%6,%7,%8,%9,%10,%11,%12,%13,%14,%15,%16,%17,%18,%19,%20,%21,%22,%23,%24,%25,%26,%27,%28,%29,%30,%31,"
      "%32,%33,%34,%35,%36,%37,%38,%39,%40,%41,%42,%43,%44,%45,%46,%47,%48,%49,%50,%51,%52,%53,%54,%55,%56,%57,%58,%59,%60,%61,%62,%63,"
      "%64,%65,%66,%67,%68,%69,%70,%71,%72,%73,%74,%75,%76,%77,%78,%79,%80,%81,%82,%83,%84,%85,%86,%87,%88,%89,%90,%91,%92,%93,%94,%95}, "
      "%96, %97, p, 1, 1, 0, 1;\n}\n"
      : R64(d, 0), R32(d, 64)
      : "l"(da), "l"(db), "r"(acc));
}
__device__ __forceinline__ void wgmma_n128(float (&d)[64], uint64_t da, uint64_t db, uint32_t acc) {
  asm volatile(
      "{\n.reg .pred p;\nsetp.ne.u32 p, %66, 0;\n"
      "wgmma.mma_async.sync.aligned.m64n128k16.f32.bf16.bf16 "
      "{%0,%1,%2,%3,%4,%5,%6,%7,%8,%9,%10,%11,%12,%13,%14,%15,%16,%17,%18,%19,%20,%21,%22,%23,%24,%25,%26,%27,%28,%29,%30,%31,"
      "%32,%33,%34,%35,%36,%37,%38,%39,%40,%41,%42,%43,%44,%45,%46,%47,%48,%49,%50,%51,%52,%53,%54,%55,%56,%57,%58,%59,%60,%61,%62,%63}, "
      "%64, %65, p, 1, 1, 0, 1;\n}\n"
      : R64(d, 0)
      : "l"(da), "l"(db), "r"(acc));
}
template <int N> __device__ __forceinline__ void fence_regs(float (&d)[N]) {
#pragma unroll
  for (int i = 0; i < N; i++) asm volatile("" : "+f"(d[i])::"memory");
}

__device__ __forceinline__ void mma16816(float (&d)[4], uint32_t a0, uint32_t a1, uint32_t a2, uint32_t a3, uint32_t b0,
                                         uint32_t b1) {
  asm("mma.sync.aligned.m16n8k16.row.col.f32.bf16.bf16.f32 {%0,%1,%2,%3}, {%4,%5,%6,%7}, {%8,%9}, {%0,%1,%2,%3};\n"
      : "+f"(d[0]), "+f"(d[1]), "+f"(d[2]), "+f"(d[3])
      : "r"(a0), "r"(a1), "r"(a2), "r"(a3), "r"(b0), "r"(b1));
}
__device__ __forceinline__ void mma16816_z(float (&d)[4], uint32_t a0, uint32_t a1, uint32_t a2, uint32_t a3, uint32_t b0,
                                           uint32_t b1) {
  asm("mma.sync.aligned.m16n8k16.row.col.f32.bf16.bf16.f32 {%0,%1,%2,%3}, {%4,%5,%6,%7}, {%8,%9}, {%10,%10,%10,%10};\n"
      : "=f"(d[0]), "=f"(d[1]), "=f"(d[2]), "=f"(d[3])
      : "r"(a0), "r"(a1), "r"(a2), "r"(a3), "r"(b0), "r"(b1), "f"(0.f));
}
__device__ __forceinline__ void ldsm4t(uint32_t (&r)[4], uint32_t a) {
  asm volatile("ldmatrix.sync.aligned.m8n8.x4.trans.shared.b16 {%0,%1,%2,%3}, [%4];\n"
               : "=r"(r[0]), "=r"(r[1]), "=r"(r[2]), "=r"(r[3]) : "r"(a) : "memory");
}
__device__ __forceinline__ void ldsm2t(uint32_t& r0, uint32_t& r1, uint32_t a) {
  asm volatile("ldmatrix.sync.aligned.m8n8.x2.trans.shared.b16 {%0,%1}, [%2];\n" : "=r"(r0), "=r"(r1) : "r"(a) : "memory");
}
__device__ __forceinline__ void st_async128(uint32_t a, uint32_t bar, uint32_t x, uint32_t y, uint32_t z, uint32_t w) {
  asm volatile("st.async.weak.shared::cluster.mbarrier::complete_tx::bytes.v4.b32 [%0], {%2,%3,%4,%5}, [%1];\n"
               ::"r"(a), "r"(bar), "r"(x), "r"(y), "r"(z), "r"(w) : "memory");
}
__device__ __forceinline__ void mbar_arrive(uint32_t a) {
  asm volatile("mbarrier.arrive.shared::cta.b64 _, [%0];\n" ::"r"(a) : "memory");
}
__device__ __forceinline__ void stsm4(uint32_t a, uint32_t r0, uint32_t r1, uint32_t r2, uint32_t r3) {
  asm volatile("stmatrix.sync.aligned.m8n8.x4.shared.b16 [%0], {%1,%2,%3,%4};\n"
               ::"r"(a), "r"(r0), "r"(r1), "r"(r2), "r"(r3) : "memory");
}
__device__ __forceinline__ void stsm4t(uint32_t a, uint32_t r0, uint32_t r1, uint32_t r2, uint32_t r3) {
  asm volatile("stmatrix.sync.aligned.m8n8.x4.trans.shared.b16 [%0], {%1,%2,%3,%4};\n"
               ::"r"(a), "r"(r0), "r"(r1), "r"(r2), "r"(r3) : "memory");
}
__device__ __forceinline__ uint2 lds64(uint32_t a) {
  uint2 v;
  asm volatile("ld.shared.v2.u32 {%0,%1}, [%2];\n" : "=r"(v.x), "=r"(v.y) : "r"(a));
  return v;
}
__device__ __forceinline__ uint4 lds128(uint32_t a) {
  uint4 v;
  asm volatile("ld.shared.v4.u32 {%0,%1,%2,%3}, [%4];\n" : "=r"(v.x), "=r"(v.y), "=r"(v.z), "=r"(v.w) : "r"(a) : "memory");
  return v;
}
__device__ __forceinline__ void sts128(uint32_t a, uint32_t x, uint32_t y, uint32_t z, uint32_t w) {
  asm volatile("st.shared.v4.u32 [%0], {%1,%2,%3,%4};\n" ::"r"(a), "r"(x), "r"(y), "r"(z), "r"(w) : "memory");
}
__device__ __forceinline__ uint32_t pack_bf16(float lo, float hi) {
  uint32_t r;
  asm("cvt.rn.bf16x2.f32 %0, %1, %2;\n" : "=r"(r) : "f"(hi), "f"(lo));
  return r;
}
__device__ __forceinline__ uint32_t bmul2(uint32_t a, uint32_t b) {
  uint32_t r;
  asm("mul.rn.bf16x2 %0, %1, %2;\n" : "=r"(r) : "r"(a), "r"(b));
  return r;
}
__device__ __forceinline__ uint32_t bmax2(uint32_t a, uint32_t b) {
  uint32_t r;
  asm("max.bf16x2 %0, %1, %2;\n" : "=r"(r) : "r"(a), "r"(b));
  return r;
}
__device__ __forceinline__ uint32_t bfma2(uint32_t a, uint32_t b, uint32_t c) {
  uint32_t r;
  asm("fma.rn.bf16x2 %0, %1, %2, %3;\n" : "=r"(r) : "r"(a), "r"(b), "r"(c));
  return r;
}
__device__ __forceinline__ uint32_t badd2(uint32_t a, uint32_t b) {
  uint32_t r;
  asm("add.rn.bf16x2 %0, %1, %2;\n" : "=r"(r) : "r"(a), "r"(b));
  return r;
}
__device__ __forceinline__ void prefetch_l2(const void* p) { asm volatile("prefetch.global.L2 [%0];\n" ::"l"(p)); }
__device__ __forceinline__ void cp_async16n(uint32_t dst, const void* src) {
  asm volatile("cp.async.cg.shared.global [%0], [%1], 16;\n" ::"r"(dst), "l"(src) : "memory");
}
__device__ __forceinline__ void cp_async16(uint32_t dst, const void* src, uint32_t srcbytes) {
  asm volatile("cp.async.cg.shared.global.L2::256B [%0], [%1], 16, %2;\n" ::"r"(dst), "l"(src), "r"(srcbytes) : "memory");
}
__device__ __forceinline__ uint32_t ld_acquire(const uint32_t* p) {
  uint32_t v;
  asm volatile("ld.acquire.gpu.global.u32 %0, [%1];\n" : "=r"(v) : "l"(p) : "memory");
  return v;
}
__device__ __forceinline__ uint32_t ld_relaxed(const uint32_t* p) {
  uint32_t v;
  asm volatile("ld.relaxed.gpu.global.u32 %0, [%1];\n" : "=r"(v) : "l"(p) : "memory");
  return v;
}
__device__ __forceinline__ void st_release(uint32_t* p, uint32_t v) {
  asm volatile("st.release.gpu.global.u32 [%0], %1;\n" ::"l"(p), "r"(v) : "memory");
}
__device__ __forceinline__ void wait_flag(const uint32_t* p, uint32_t want) {
  int n = 0;
  while (ld_relaxed(p) != want && ++n < SPIN_LIMIT) __nanosleep(40);
  (void)ld_acquire(p);
}

struct Params {
  const __nv_bfloat16* x;
  const __nv_bfloat16* w;
  const __nv_bfloat16* q;
  const __nv_bfloat16* k;
  const __nv_bfloat16* v;
  const __nv_bfloat16* shift_k;
  const __nv_bfloat16* ssm_k;
  const __nv_bfloat16* ssm_D;
  const __nv_bfloat16* wo;
  __nv_bfloat16* out;
};

__device__ __forceinline__ uint32_t lds32(uint32_t a) {
  uint32_t v;
  asm volatile("ld.shared.u32 %0, [%1];\n" : "=r"(v) : "r"(a));
  return v;
}
#define W4(d, o) "=f"(d[o + 0]), "=f"(d[o + 1]), "=f"(d[o + 2]), "=f"(d[o + 3])
#define W8(d, o) W4(d, o), W4(d, o + 4)
#define W16(d, o) W8(d, o), W8(d, o + 8)
#define U4(c, d, o) c(d[o + 0]), c(d[o + 1]), c(d[o + 2]), c(d[o + 3])
#define U8(c, d, o) U4(c, d, o), U4(c, d, o + 4)
#define U16(c, d, o) U8(c, d, o), U8(c, d, o + 8)
#define U32(c, d, o) U16(c, d, o), U16(c, d, o + 16)
#define D32 "{%0,%1,%2,%3,%4,%5,%6,%7,%8,%9,%10,%11,%12,%13,%14,%15,%16,%17,%18,%19,%20,%21,%22,%23,%24,%25,%26,%27,%28,%29,%30,%31}"
#define D16 "{%0,%1,%2,%3,%4,%5,%6,%7,%8,%9,%10,%11,%12,%13,%14,%15}"
#define D8 "{%0,%1,%2,%3,%4,%5,%6,%7}"
template <int ACC> __device__ __forceinline__ void hmma_n128t(uint32_t (&d)[32], const uint32_t (&a)[4], uint64_t db) {
  if (ACC)
    asm volatile("wgmma.mma_async.sync.aligned.m64n128k16.f16.f16.f16 " D32 ", {%32,%33,%34,%35}, %36, 1, 1, 1, 1;\n"
                 : U32("+r", d, 0) : "r"(a[0]), "r"(a[1]), "r"(a[2]), "r"(a[3]), "l"(db));
  else
    asm volatile("wgmma.mma_async.sync.aligned.m64n128k16.f16.f16.f16 " D32 ", {%32,%33,%34,%35}, %36, 0, 1, 1, 1;\n"
                 : U32("=r", d, 0) : "r"(a[0]), "r"(a[1]), "r"(a[2]), "r"(a[3]), "l"(db));
}
template <int ACC, int TB> __device__ __forceinline__ void hmma_n32(uint32_t (&d)[8], const uint32_t (&a)[4], uint64_t db) {
  if (ACC)
    asm volatile("wgmma.mma_async.sync.aligned.m64n32k16.f16.f16.f16 " D8 ", {%8,%9,%10,%11}, %12, 1, 1, 1, %13;\n"
                 : U8("+r", d, 0) : "r"(a[0]), "r"(a[1]), "r"(a[2]), "r"(a[3]), "l"(db), "n"(TB));
  else
    asm volatile("wgmma.mma_async.sync.aligned.m64n32k16.f16.f16.f16 " D8 ", {%8,%9,%10,%11}, %12, 0, 1, 1, %13;\n"
                 : U8("=r", d, 0) : "r"(a[0]), "r"(a[1]), "r"(a[2]), "r"(a[3]), "l"(db), "n"(TB));
}
template <int N> __device__ __forceinline__ void fence_regs(uint32_t (&d)[N]) {
#pragma unroll
  for (int i = 0; i < N; i++) asm volatile("" : "+r"(d[i])::"memory");
}
__device__ __forceinline__ uint32_t hmul(uint32_t a, uint32_t b) { uint32_t r; asm("mul.rn.f16x2 %0, %1, %2;\n" : "=r"(r) : "r"(a), "r"(b)); return r; }
__device__ __forceinline__ uint32_t hadd(uint32_t a, uint32_t b) { uint32_t r; asm("add.rn.f16x2 %0, %1, %2;\n" : "=r"(r) : "r"(a), "r"(b)); return r; }
__device__ __forceinline__ uint32_t hsub(uint32_t a, uint32_t b) { uint32_t r; asm("sub.rn.f16x2 %0, %1, %2;\n" : "=r"(r) : "r"(a), "r"(b)); return r; }
__device__ __forceinline__ uint32_t hfma(uint32_t a, uint32_t b, uint32_t c) { uint32_t r; asm("fma.rn.f16x2 %0, %1, %2, %3;\n" : "=r"(r) : "r"(a), "r"(b), "r"(c)); return r; }
__device__ __forceinline__ uint32_t hfnma(uint32_t a, uint32_t b, uint32_t c) {
  uint32_t r;
  asm("{\n.reg .b32 t;\nneg.f16x2 t, %1;\nfma.rn.f16x2 %0, t, %2, %3;\n}\n" : "=r"(r) : "r"(a), "r"(b), "r"(c));
  return r;
}
__device__ __forceinline__ uint32_t hrefl(uint32_t p, uint32_t s) {
  uint32_t r;
  asm("{\n.reg .b32 t;\nneg.f16x2 t, %2;\nfma.rn.f16x2 %0, %1, %3, t;\n}\n" : "=r"(r) : "r"(p), "r"(s), "r"(0x40004000u));
  return r;
}
__device__ __forceinline__ void bfly(uint32_t xr, uint32_t xi, uint32_t tr, uint32_t ti, uint32_t yr, uint32_t yi, uint32_t ur,
                                     uint32_t ui, uint32_t& sr, uint32_t& si, uint32_t& dr, uint32_t& di) {
  const uint32_t pr = hfnma(xi, ti, hmul(xr, tr)), pi = hfma(xi, tr, hmul(xr, ti));
  sr = hfnma(yi, ui, hfma(yr, ur, pr));
  si = hfma(yi, ur, hfma(yr, ui, pi));
  dr = hrefl(pr, sr);
  di = hrefl(pi, si);
}
template <int BH> __device__ __forceinline__ void fft_e1(const uint32_t (&d)[32], const uint32_t (&tw)[16], uint32_t (&a2)[2][2][4]) {
#pragma unroll
  for (int be = 0; be < 2; be++)
#pragma unroll
    for (int s = 0; s < 2; s++) {
      const int o = 16 * s + 8 * be + 2 * BH, p = 2 * BH;
      bfly(d[o], d[o + 1], tw[p], tw[p + 1], d[o + 4], d[o + 5], tw[p + 4], tw[p + 5], a2[be][0][s], a2[be][0][2 + s],
           a2[be][1][s], a2[be][1][2 + s]);
    }
}
__device__ __forceinline__ uint32_t hfms(uint32_t a, uint32_t b, uint32_t c) {
  uint32_t r;
  asm("{\n.reg .b32 t;\nneg.f16x2 t, %3;\nfma.rn.f16x2 %0, %1, %2, t;\n}\n" : "=r"(r) : "r"(a), "r"(b), "r"(c));
  return r;
}
template <int C, int J> __device__ __forceinline__ void fft_e2(const uint32_t (&d0)[8], const uint32_t (&d1)[8], uint32_t (&a3)[2][4]) {
  const uint32_t ur = d0[2 * J], ui = d0[4 + 2 * J], hr = d0[2 * J + 1], hi = d0[5 + 2 * J];
  const uint32_t vr = d1[2 * J], vi = d1[4 + 2 * J], gr = d1[2 * J + 1], gi = d1[5 + 2 * J];
  const uint32_t pr = hfnma(ui, hi, hmul(ur, hr)), pi = hfma(ui, hr, hmul(ur, hi));
  a3[0][2 + C] = pr;
  a3[0][C] = pi;
  a3[1][2 + C] = hfnma(vi, hi, hfma(vr, hr, hfnma(ui, gi, hfms(ur, gr, pi))));
  a3[1][C] = hfma(vi, hr, hfma(vr, hi, hfma(ui, gr, hfma(ur, gi, pr))));
}
__device__ __forceinline__ void fft_e3(const uint32_t (&d)[2][8], const uint32_t (&tw)[16], uint32_t zaddr) {
#pragma unroll
  for (int rho = 0; rho < 2; rho++) {
    uint32_t zr[4], zi[4];
#pragma unroll
    for (int nb = 0; nb < 4; nb++) {
      const uint32_t xi = d[nb >> 1][2 * (nb & 1) + rho], xr = d[nb >> 1][4 + 2 * (nb & 1) + rho];
      const uint32_t tr = tw[8 + 4 * rho + 2 * (nb & 1)], ti = tw[9 + 4 * rho + 2 * (nb & 1)];
      zr[nb] = hfnma(xi, ti, hmul(xr, tr));
      zi[nb] = hfma(xi, tr, hmul(xr, ti));
    }
    stsm4(zaddr + rho * 1024, zr[0], zr[1], zr[2], zr[3]);
    stsm4(zaddr + rho * 1024 + 512, zi[0], zi[1], zi[2], zi[3]);
  }
}
__device__ __forceinline__ float bf_lo(uint32_t v) {
  uint32_t r;
  asm("prmt.b32 %0, %1, 0, 0x1044;\n" : "=r"(r) : "r"(v));
  return __uint_as_float(r);
}
__device__ __forceinline__ float bf_hi(uint32_t v) { return __uint_as_float(v & 0xffff0000u); }
__device__ __forceinline__ float ex2(float x) {
  float r;
  asm("ex2.approx.ftz.f32 %0, %1;\n" : "=f"(r) : "f"(x));
  return r;
}
__device__ __forceinline__ float rcp(float x) {
  float r;
  asm("rcp.approx.ftz.f32 %0, %1;\n" : "=f"(r) : "f"(x));
  return r;
}

__device__ __forceinline__ int g2_a(int s) { return ((0xA1054 >> (4 * s)) & 15) * 16384; }
__device__ __forceinline__ int g2_b(int s) { return ((0xCDB32 >> (4 * s)) & 15) * 16384; }
static_assert(OFF_U == 10 * 16384 && OFF_H == 12 * 16384 && OFF_OP == 4 * 16384, "units");
__device__ __forceinline__ int g2_k(int hp, int i) {
  return i < 2 ? hp ^ 1 ^ i : i < 4 ? (hp & ~1) ^ i : ((hp & ~3) + i) & 15; }
__device__ __forceinline__ int y_slot(int wg, int it) {
  static_assert(T_B2 == T_TW + 8192 && T_A1 == T_B2 + 4096, "y slots");
  return OFF_T + T_TW + ((it + 3) & 3) * 4096 + wg * 2048;
}

__device__ __forceinline__ void to_arr(uint32_t (&d)[4], uint4 v) { d[0] = v.x; d[1] = v.y; d[2] = v.z; d[3] = v.w; }

__device__ __forceinline__ void attn_stage(uint32_t sb, int blk, int lane, const float (&acc)[96], uint32_t (&k1)[2][4]) {
  const int lr = lane & 7, lm = lane >> 3;
  const uint32_t base = sb + OFF_VP + (blk * 16 + lr + 8 * (lm & 1)) * 128;
#pragma unroll
  for (int i = 0; i < 8; i++) k1[i >> 2][i & 3] = pack_bf16(acc[34 + 4 * i], acc[35 + 4 * i]);
  const uint32_t kh = sb + OFF_KH + blk * 2048 + lane * 16;
  sts128(kh, k1[0][0], k1[0][1], k1[0][2], k1[0][3]);
  sts128(kh + 512, k1[1][0], k1[1][1], k1[1][2], k1[1][3]);
#pragma unroll
  for (int j = 0; j < 8; j += 2)
    stsm4(base + (((j + (lm >> 1)) ^ lr) << 4), pack_bf16(acc[64 + 4 * j], acc[65 + 4 * j]),
          pack_bf16(acc[66 + 4 * j], acc[67 + 4 * j]), pack_bf16(acc[68 + 4 * j], acc[69 + 4 * j]),
          pack_bf16(acc[70 + 4 * j], acc[71 + 4 * j]));
}
__device__ __forceinline__ void attn_pack(const float (&acc)[96], uint32_t (&qa)[2][8], uint32_t (&k0)[2][4]) {
#pragma unroll
  for (int hd = 0; hd < 2; hd++) {
#pragma unroll
    for (int i = 0; i < 8; i++) {
      asm volatile("cvt.rn.bf16x2.f32 %0, %1, %2;\n" : "=r"(qa[hd][i]) : "f"(acc[16 * hd + 2 * i + 1]), "f"(acc[16 * hd + 2 * i]));
    }
#pragma unroll
    for (int i = 0; i < 4; i++) {
      asm volatile("cvt.rn.bf16x2.f32 %0, %1, %2;\n" : "=r"(k0[hd][i]) : "f"(acc[33 + 16 * hd + 4 * i]), "f"(acc[32 + 16 * hd + 4 * i]));
    }
  }
}
__device__ __forceinline__ void attn_own(const uint32_t (&k0)[2][4], const uint32_t (&k1)[2][4], bool le0, bool le1,
                                         const uint32_t (&qa)[2][8], float (&l)[2][4]) {
#pragma unroll
  for (int hd = 0; hd < 2; hd++) {
    float s0[4], s1[4];
    mma16816_z(s0, qa[hd][0], qa[hd][1], qa[hd][2], qa[hd][3], k0[hd][0], k0[hd][1]);
    mma16816_z(s1, qa[hd][0], qa[hd][1], qa[hd][2], qa[hd][3], k1[hd][0], k1[hd][1]);
    mma16816(s0, qa[hd][4], qa[hd][5], qa[hd][6], qa[hd][7], k0[hd][2], k0[hd][3]);
    mma16816(s1, qa[hd][4], qa[hd][5], qa[hd][6], qa[hd][7], k1[hd][2], k1[hd][3]);
    l[hd][0] = s0[0];
    l[hd][1] = s0[1];
    l[hd][2] = le0 ? s1[2] : s0[2];
    l[hd][3] = le1 ? s1[3] : s0[3];
  }
}
template <int N> __device__ __forceinline__ void quad_softmax(float (&x)[N][2], uint32_t (&pp)[N]) {
  const float c2 = 1.4426950408889634f;
  uint32_t q[N], mx[N / 2];
#pragma unroll
  for (int n = 0; n < N; n++) {
    const uint32_t r = pack_bf16(x[n][0], x[n][1]);
    q[n] = bfma2(r, 0x3e353e35u, bmul2(r, 0x379e379eu));
    x[n][0] = bf_lo(q[n]);
    x[n][1] = bf_hi(q[n]);
  }
#pragma unroll
  for (int n = 0; n < N / 2; n++)
    mx[n] = bmax2(__byte_perm(q[2 * n], q[2 * n + 1], 0x5410), __byte_perm(q[2 * n], q[2 * n + 1], 0x7632));
#pragma unroll
  for (int o = 1; o <= 2; o++)
#pragma unroll
    for (int n = 0; n < N / 2; n++) mx[n] = bmax2(mx[n], __shfl_xor_sync(0xffffffffu, mx[n], o));
  float m[N], t[N];
#pragma unroll
  for (int n = 0; n < N / 2; n++) {
    m[2 * n] = bf_lo(mx[n]);
    m[2 * n + 1] = bf_hi(mx[n]);
  }
#pragma unroll
  for (int n = 0; n < N; n++) {
    const float nm = -m[n] * c2;
    x[n][0] = ex2(fmaf(x[n][0], c2, nm));
    x[n][1] = ex2(fmaf(x[n][1], c2, nm));
    t[n] = x[n][0] + x[n][1];
  }
#pragma unroll
  for (int o = 1; o <= 2; o++)
#pragma unroll
    for (int n = 0; n < N; n++) t[n] += __shfl_xor_sync(0xffffffffu, t[n], o);
#pragma unroll
  for (int n = 0; n < N; n++) {
    const float inv = rcp(t[n]);
    pp[n] = pack_bf16(x[n][0] * inv, x[n][1] * inv);
  }
}
__device__ __forceinline__ void attn_pv(uint32_t dst, const uint32_t (&va)[4], const uint32_t (&vb)[4], uint32_t pp,
                                        uint32_t maskLE) {
  const uint32_t b0 = pp & ~maskLE, b1 = pp & maskLE;
  float oa[4], ob[4];
  mma16816_z(oa, va[0], va[1], va[2], va[3], b0, b1);
  mma16816_z(ob, vb[0], vb[1], vb[2], vb[3], b0, b1);
  stsm4t(dst, pack_bf16(oa[0], oa[1]), pack_bf16(oa[2], oa[3]), pack_bf16(ob[0], ob[1]), pack_bf16(ob[2], ob[3]));
}

template <int MODE>
__global__ void __cluster_dims__(2, 1, 1) __launch_bounds__(NTHREADS, 1)
fused_kernel(const Params p, const __grid_constant__ CUtensorMap tmX, const __grid_constant__ CUtensorMap tmW,
             const __grid_constant__ CUtensorMap tmWo,
             const __grid_constant__ CUtensorMap tmQ,
             const __grid_constant__ CUtensorMap tmXh, const __grid_constant__ CUtensorMap tmWh) {
  extern __shared__ __align__(1024) uint8_t smem[];
  const uint32_t sb = smem_u32(smem) - OFF_L0;
  const uint32_t bars = sb + OFF_BAR;
  const int tid = threadIdx.x, lane = tid & 31, warp = __shfl_sync(0xffffffffu, tid >> 5, 0);
  const int rank = blockIdx.x & 1;
  const bool halo_cta = blockIdx.x < 4;
  if (halo_cta && MODE != 0) return;
  int grp, mem;
  {
    const int t = (blockIdx.x >> 1) - 4, u = t - 32;
    const int q7 = (u * 37) >> 8;
    const bool lo = (unsigned)t < 32u, mid = (unsigned)u < 28u;
    grp = lo ? (t & 7) : (mid ? 1 + u - 7 * q7 : 0);
    mem = lo ? (t >> 3) : (mid ? 4 + q7 : (t < 0 ? t + 6 : t - 54));
  }
  const int rg = (grp >> 2) * 4 + (mem >> 1), hp = (grp & 3) * 4 + (mem & 1) * 2 + rank;
  const int rb2 = (grp >> 2) * 8 + mem, cb2 = (grp & 3) * 2 + rank;
  const int chb = grp * 16 + mem * 2 + rank;
  const int cta = rg * 16 + hp;
  const int par = rg >> 2, gidx = rg & 3;

  if (tid < 256 && !halo_cta && MODE != 2) {
    const int r = tid >> 3, c = tid & 7;
    const uint32_t so = r * 128 + ((c ^ (r & 7)) << 4);
    const __nv_bfloat16* wg0 = p.w + (size_t)r * (3 * DM) + hp * 64 + c * 8;
    const __nv_bfloat16* xg0 = p.x + (size_t)(2 * (gidx * 256 + r) + par) * DM + c * 8;
#pragma unroll
    for (int j = 0; j < 3; j++) cp_async16n(sb + OFF_1B + j * 4096 + so, wg0 + j * DM);
#pragma unroll
    for (int i = 0; i < 8; i++) cp_async16n(sb + i * 4096 + so, xg0 + (size_t)i * 64 * DM);
    asm volatile("cp.async.commit_group;\n" ::: "memory");
  }
  if (tid == 256) {
    prefetch_tmap(halo_cta ? &tmXh : &tmX);
#pragma unroll
    for (int i = 0; i < NS1B; i++) mbar_init(bars + 8 * (BAR_FULLB + i), 1);
#pragma unroll
    for (int i = 0; i < NS1A; i++) mbar_init(bars + 8 * (BAR_FULLA + i), 1);
    asm volatile("fence.mbarrier_init.release.cluster;\n" ::: "memory");
    if (!halo_cta && MODE != 2) {
      mbar_expect_tx(bars + 8 * (BAR_FULLB + 1), STG1B);
      tma_load_3d(sb + OFF_1B + 1 * STG1B, &tmW, bars + 8 * (BAR_FULLB + 1), hp * 64, 32, 0);
      mbar_expect_tx(bars + 8 * (BAR_FULLB + 2), STG1B);
      tma_load_3d(sb + OFF_1B + 2 * STG1B, &tmW, bars + 8 * (BAR_FULLB + 2), hp * 64, 64, 0);
    } else {
      prefetch_tmap(&tmWh);
    }
  } else if (tid == 288) {
#pragma unroll
    for (int i = 0; i < NS1A; i++) mbar_init(bars + 8 * (BAR_EMPTYA + i), 4);
#pragma unroll
    for (int i = 0; i < NS1B; i++) mbar_init(bars + 8 * (BAR_EMPTYB + i), 2);
    asm volatile("fence.mbarrier_init.release.cluster;\n" ::: "memory");
  } else if (tid == 320) {
#pragma unroll
    for (int i = 0; i < NS2; i++) {
      mbar_init(bars + 8 * (BAR_FULL2 + i), 1);
      mbar_init(bars + 8 * (BAR_EMPTY2 + i), 4);
    }
    mbar_init(bars + 8 * BAR_DEAD, 2);
    mbar_init(bars + 8 * (BAR_DEAD + 1), 2);
    mbar_init(bars + 8 * BAR_X, 2);
    mbar_init(bars + 8 * BAR_REL, 2);
    asm volatile("fence.mbarrier_init.release.cluster;\n" ::: "memory");
  } else if (tid == 352) {
    mbar_init(bars + 8 * BAR_T, 1);
    mbar_init(bars + 8 * BAR_UH, 3);
    mbar_init(bars + 8 * BAR_LFREE, 4);
    mbar_init(bars + 8 * BAR_LAND, 1);
    mbar_init(bars + 8 * BAR_U, 1);
    mbar_init(bars + 8 * BAR_Q, 1);
    mbar_init(bars + 8 * BAR_STG, 9);
    asm volatile("fence.mbarrier_init.release.cluster;\n" ::: "memory");
  }
  if (warp == 8) PROF2(23);
  cluster_sync_all();
  if (warp == 8) PROF2(24);

  if (warp >= 8) {
    const int hw = warp - 8;
    const int lr = lane & 7, lm = lane >> 3;
    auto g1_issue_a = [&](int j, int s) {
      const uint32_t fb = bars + 8 * (BAR_FULLA + s);
      mbar_expect_tx(fb, STG1A);
      tma_load_3d_mc(sb + s * STG1A + rank * 16384, &tmX, fb, j * 64, par, gidx * 256 + rank * 128);
    };
    auto g1_issue_b = [&](int kb, int s) {
      const uint32_t fb = bars + 8 * (BAR_FULLB + s);
      mbar_expect_tx(fb, STG1B);
      tma_load_3d(sb + OFF_1B + s * STG1B, &tmW, fb, hp * 64, kb * 32, 0);
    };
    asm volatile("setmaxnreg.dec.sync.aligned.u32 %0;\n" :: "n"(REG_HELP));

    if (halo_cta) {
      if (hw == 0) {
        int s = 0, ph = 1;
#pragma unroll 1
        for (int kb = 0; kb < 16; kb++) {
          mbar_wait(bars + 8 * (BAR_EMPTYB + s), ph);
          const uint32_t fb = bars + 8 * (BAR_FULLB + s), st = sb + s * STGH;
          if (elect_one()) {
            mbar_expect_tx(fb, STGH);
            tma_load_4d(st, &tmXh, fb, kb * 64, 248, 0, 0);
            tma_load_3d(st + 8192, &tmWh, fb, 0, kb * 64, 16 + blockIdx.x * 4);
            tma_load_3d(st + 8192 + 32768, &tmWh, fb, 0, kb * 64, 32 + blockIdx.x * 4);
          }
          if (++s == 3) { s = 0; ph ^= 1; }
        }
      }
      __syncwarp();
    } else if (hw == 0) {
      uint32_t epoch = 0;
      if (lane < (MODE == 2 ? NS2 : 2)) mbar_arrive_cluster_n(mapa(bars, rank) + 8 * (BAR_EMPTY2 + lane), 4);
      if (MODE != 2) {
      epoch = ld_relaxed(g_flag_o + 2 * cta) + 1;
      if (lane == 0) {
        mbar_expect_tx(bars + 8 * BAR_U, 32768);
        mbar_expect_tx(bars + 8 * BAR_LAND, 32768 + 64);
        mbar_expect_tx(bars + 8 * BAR_Q, 32768);
        mbar_expect_tx(bars + 8 * BAR_T, T_END);
      }
      {
        int sa = 1, pha = 1, sbb = 2, phb = 1;
#pragma unroll 1
        for (int kb = 2; kb < 32; kb++) {
          if (!(kb & 1)) {
            mbar_wait(bars + 8 * (BAR_EMPTYA + sa), pha);
            if (elect_one()) g1_issue_a(kb >> 1, sa);
            if (++sa == NS1A) { sa = 0; pha ^= 1; }
          }
          mbar_wait(bars + 8 * (BAR_EMPTYB + sbb), phb);
          if (kb > 2 && elect_one()) g1_issue_b(kb, sbb);
          __syncwarp();
          if (kb >= PF0 && kb < PF0 + 12)
            prefetch_l2((kb < PF0 + 8 ? p.q + (size_t)chb * 16384 + (kb - PF0) * 2048 : p.wo + (size_t)chb * 8192 + (kb - PF0 - 8) * 2048) + lane * 64);
          if (kb == 4) PROF2(27);
          if (kb == 1) PROF2(38);
          if (kb == 2) PROF2(39);
          if (++sbb == NS1B) { sbb = 0; phb ^= 1; }
        }
      }
      static_assert(32 % NS1B == 2 && (32 / NS1B) % 2 == 0 && OFF_Q == OFF_1B && 2 * STG1B == 6 * 4096, "slots / parity of these loads");
      const uint8_t* tab = reinterpret_cast<const uint8_t*>(g_tab);
      if (lane == 0) {
        prefetch_tmap(&tmWo);
        prefetch_tmap(&tmQ);
        bulk_load(sb + OFF_T + T_A1, tab + T_A1, T_END - T_A1, bars + 8 * BAR_T);
        mbar_wait(bars + 8 * (BAR_EMPTYB + 2), 1);
        tma_load_5d(sb + OFF_Q + 6 * 4096, &tmQ, bars + 8 * BAR_Q, (chb & ~1) * 8, rank * 32 + 24);
        tma_load_5d(sb + OFF_Q + 7 * 4096, &tmQ, bars + 8 * BAR_Q, (chb & ~1) * 8, rank * 32 + 28);
        if (gidx != 0) wait_flag(g_flag_h + (hp >> 2), epoch);
      }
      __syncwarp();
      {
        uint4 hk0 = make_uint4(0, 0, 0, 0), hk1 = hk0, hv0 = hk0, hv1 = hk0;
        if (gidx != 0) {
          const uint4* src = g_halo + cta * 128 + lane;
          hk0 = __ldcg(src); hk1 = __ldcg(src + 32); hv0 = __ldcg(src + 64); hv1 = __ldcg(src + 96);
        }
        if (lane == 0) {
          mbar_wait(bars + 8 * (BAR_EMPTYB + 3), 1);
          bulk_load(sb + OFF_T, tab, T_TW, bars + 8 * BAR_T);
        }
        __syncwarp();
        PROF2(18);
        sts128(sb + OFF_L0 + lane * 16, hk0.x, hk0.y, hk0.z, hk0.w);
        sts128(sb + OFF_L0 + 512 + lane * 16, hk1.x, hk1.y, hk1.z, hk1.w);
        stsm4(sb + OFF_L0 + 1024 + lr * 128 + ((lm ^ lr) << 4), hv0.x, hv0.y, hv0.z, hv0.w);
        stsm4(sb + OFF_L0 + 1024 + lr * 128 + (((4 + lm) ^ lr) << 4), hv1.x, hv1.y, hv1.z, hv1.w);
        __syncwarp();
        if (lane == 0) {
          mbar_arrive(bars + 8 * BAR_STG);
          mbar_wait(bars + 8 * (BAR_EMPTYB + 4), 1);
          bulk_load(sb + OFF_T + T_TW, tab + T_TW, T_A1 - T_TW, bars + 8 * BAR_T);
          mbar_wait(bars + 8 * BAR_EMPTYB, 0);
#pragma unroll 1
          for (int i = 0; i < 6; i++) tma_load_5d(sb + OFF_Q + i * 4096, &tmQ, bars + 8 * BAR_Q, (chb & ~1) * 8, rank * 32 + i * 4);
        }
        __syncwarp();
      }
      }
      if (MODE != 1) {
        auto korder = [&](int i) { return MODE == 2 ? i : g2_k(hp, i); };
        const __nv_bfloat16* osrc = g_o + (size_t)(rb2 >> 1) * 16 * 16384 + ((rb2 & 1) * 2 + rank) * 4096;
        const uint32_t* flag = g_flag_o + (rb2 >> 1) * 32 + korder(lane & 15) * 2 + (rb2 & 1);
        uint32_t ready = MODE == 0 ? 0u : ~0u, pv = 0;
        auto look = [&]() {
          ready |= __ballot_sync(0xffffffffu, pv == epoch);
          asm volatile("fence.acquire.gpu;\n" ::: "memory");
          fence_async_all();
        };
        if (MODE == 0) {
          mbar_wait_idle(bars + 8 * BAR_REL, 0);
          if (POLL1) pv = ld_relaxed(flag);
          if (elect_one()) {
            mbar_expect_tx(bars + 8 * BAR_FULL2, STG2);
            tma_load_3d(sb + g2_b(0), &tmWo, bars + 8 * BAR_FULL2, 0, korder(0) * 64, cb2 * 2);
            tma_load_3d(sb + g2_b(1), &tmWo, bars + 8 * (BAR_FULL2 + 1), 0, korder(1) * 64, cb2 * 2);
          }
          if (POLL1) look();
        }
#pragma unroll
        for (int i = MODE == 0 ? 2 : 0; i < 16; i++) {
          const int kb = korder(i), s = i % NS2, ph = (i / NS2) & 1;
          const uint32_t fb = bars + 8 * (BAR_FULL2 + s);
          if (!((ready >> i) & 1)) {
            int n = 0;
            do {
              ready |= __ballot_sync(0xffffffffu, ld_acquire(flag) == epoch);
            } while (!((ready >> i) & 1) && ++n < SPIN_LIMIT);
            fence_async_all();
          }
          if (i == 2) PROF(21);
          mbar_wait(bars + 8 * (BAR_EMPTY2 + s), ph);
          if (elect_one()) {
            mbar_expect_tx(fb, STG2);
            asm volatile(
                "cp.async.bulk.shared::cluster.global.mbarrier::complete_tx::bytes.multicast::cluster [%0], [%1], %2, [%3], %4;\n"
                ::"r"(sb + g2_a(s) + rank * 8192), "l"(osrc + kb * 16384), "r"(8192), "r"(fb), "h"((uint16_t)3) : "memory");
            if (MODE != 0 || i >= 4) tma_load_3d(sb + g2_b(s), &tmWo, fb, 0, kb * 64, cb2 * 2);
          }
          if (MODE == 0 && i == LA0) pv = ld_relaxed(flag);
          if (MODE == 0 && i == LA1) look();
          if (i == 3) PROF(37);

        }
      }
      __syncwarp();
    } else if (MODE != 2) {
      {
        const int g = lane >> 2, t = lane & 3;
        uint32_t w[2][4];
#pragma unroll
        for (int h = 0; h < 2; h++) {
          const uint2 x = __ldg(reinterpret_cast<const uint2*>(p.shift_k + ((chb & ~1) * 8 + h * 8 + g) * 4));
          w[h][0] = __byte_perm(x.x, x.x, 0x1010);
          w[h][1] = __byte_perm(x.x, x.x, 0x3232);
          w[h][2] = __byte_perm(x.y, x.y, 0x1010);
          w[h][3] = __byte_perm(x.y, x.y, 0x3232);
        }
        auto swz = [](int r) { return (((r & 29) | ((r ^ (r >> 2)) & 2)) << 5) | (r & 16); };
        const uint32_t kring = sb + OFF_H + (hw - 1) * 8192, vring = kring + 4096;
        const int s0 = rank * 32 + (hw - 1) * 11, s1 = hw == 3 ? rank * 32 + 32 : s0 + 11;
        const size_t goff = (size_t)(lane >> 1) * DM + (chb & ~1) * 8 + (lane & 1) * 8;
        const __nv_bfloat16* kg = p.k + goff;
        const __nv_bfloat16* vg = p.v + goff;
        const uint32_t d0 = swz(lane >> 1) ^ ((lane & 1) << 4), d1 = swz(16 + (lane >> 1)) ^ ((lane & 1) << 4);
        auto issue = [&](int st) {
          const uint32_t so = (st & 3) << 10;
          cp_async16(kring + so + d0, kg + (size_t)st * 32 * DM, 16);
          cp_async16(kring + so + d1, kg + (size_t)(st * 32 + 16) * DM, 16);
          cp_async16(vring + so + d0, vg + (size_t)st * 32 * DM, 16);
          cp_async16(vring + so + d1, vg + (size_t)(st * 32 + 16) * DM, 16);
        };
        const int xa = 8 * (lr >> 1) + 2 * lm + (lr & 1), xb = 8 * (lr >> 1) - 4 + 2 * (lm & 1) + (lr & 1);
        const uint32_t la = swz(xa), lb = swz(xb & 31);
        const int backb = xb < 0 ? 1 : 0;
        const uint32_t ud[2] = {mapa(sb + OFF_U + g * 4096 + t * 16, 0), mapa(sb + OFF_U + g * 4096 + t * 16, 1)};
        const uint32_t ub[2] = {mapa(bars + 8 * BAR_U, 0), mapa(bars + 8 * BAR_U, 1)};
        if (lane == 0) mbar_wait(bars + 8 * (BAR_FULLB + NS1B - 1), 0);
        __syncwarp();
        if (lane >= 24) cp_async16(kring + (((s0 - 1) & 3) << 10) + d1, s0 > 0 ? kg + (size_t)(s0 * 32 - 16) * DM : kg, s0 > 0 ? 16 : 0);
        issue(s0);
        asm volatile("cp.async.commit_group;\n" ::: "memory");
        issue(s0 + 1);
        asm volatile("cp.async.commit_group;\n" ::: "memory");
#pragma unroll 1
        for (int st = s0; st < s1; st++) {
          if (st + 2 < s1) issue(st + 2);
          if (hw == 1 && st - s0 < 8) prefetch_l2(p.ssm_k + (size_t)(chb * 8 + st - s0) * SEQ + lane * 64);
          if (hw == 2 && st == s0 + 4 && lane < 2) prefetch_l2(g_tab + (chb * 2 + lane) * 32);
          const uint32_t uo = (st ^ ((g ^ (st >> 2)) & 1)) * 64;
          asm volatile("cp.async.commit_group;\n" ::: "memory");
          asm volatile("cp.async.wait_group 2;\n" ::: "memory");
          __syncwarp();
#pragma unroll
          for (int h = 0; h < 2; h++) {
            uint32_t e[6], vv[4], e4[4];
            ldsm4t(e4, kring + ((st & 3) << 10) + (la ^ (h << 4)));
            ldsm2t(e[0], e[1], kring + (((st - backb) & 3) << 10) + (lb ^ (h << 4)));
            ldsm4t(vv, vring + ((st & 3) << 10) + (la ^ (h << 4)));
            e[2] = e4[0]; e[3] = e4[1]; e[4] = e4[2]; e[5] = e4[3];
            uint32_t o[5];
#pragma unroll
            for (int i = 0; i < 5; i++) o[i] = __byte_perm(e[i], e[i + 1], 0x5432);
#pragma unroll
            for (int i = 0; i < 4; i++) {
              uint32_t a = bmul2(o[i], w[h][3]);
              a = bfma2(e[i + 1], w[h][2], a);
              a = bfma2(o[i + 1], w[h][1], a);
              a = bfma2(e[i + 2], w[h][0], a);
              vv[i] = bmul2(a, vv[i]);
            }
            st_async128(ud[h] + uo, ub[h], vv[0], vv[1], vv[2], vv[3]);
          }
          __syncwarp();
        }
        PROF(16);
      }
      {
        const int rw = (lane >> 3) + (lane & 4), ck = lane & 3;
        const uint32_t so = rw * 64 + ck * 16, dof = rw * 128 + ((ck ^ rw) << 4);
        const uint8_t* hsrc = reinterpret_cast<const uint8_t*>(p.ssm_k + (size_t)chb * 8 * SEQ) + so;
        const float dv = lane < 8 ? __bfloat162float(p.ssm_D[chb * 8 + lane]) : 0.f;
        uint32_t x[32];
        auto load = [&](const uint8_t* src, int i) {
          asm volatile("ld.v4.u32 {%0,%1,%2,%3}, [%4];\n" : "=r"(x[4 * i]), "=r"(x[4 * i + 1]), "=r"(x[4 * i + 2]), "=r"(x[4 * i + 3])
                       : "l"(src + i * 512) : "memory");
        };
#pragma unroll
        for (int i = 0; i < 8; i++) load(hsrc + (hw - 1) * 4096, i);
        nb_sync(NB_HELP3, 96);
        mbar_wait(bars + 8 * BAR_U, 0);
        int eh = 0;
#pragma unroll 1
        for (int n = 2 * (hw - 1); n < 16; n += (n & 1) ? 5 : 1) {
          const int c = n >> 1;
          const uint8_t* nsrc = (n & 1) ? hsrc + (c < 5 ? c + 3 : c) * 4096
                                        : smem - OFF_L0 + OFF_U + c * 4096 + (so ^ (((c ^ (lane >> 2)) & 1) << 6));
          const uint32_t dst = sb + ((n & 1) ? OFF_U : OFF_H) + c * 4096 + dof;
          const float dc = __shfl_sync(0xffffffffu, dv, c);
          const float h0 = bf_lo(x[0]) + ((lane | (n & 1)) == 0 ? dc : 0.f), h1 = bf_hi(x[0]);
          x[0] = pack_bf16(h0, h1);
          uint32_t m[2] = {x[0], x[1]};
#pragma unroll
          for (int i = 2; i < 32; i++) asm("max.xorsign.abs.bf16x2 %0, %0, %1;\n" : "+r"(m[i & 1]) : "r"(x[i]));
          asm("max.xorsign.abs.bf16x2 %0, %0, %1;\n" : "+r"(m[0]) : "r"(m[1]));
          const uint32_t e = max(__reduce_max_sync(0xffffffffu, max((m[0] >> 7) & 255u, (m[0] >> 23) & 255u)), 5u);
          const uint32_t sc = (259u - e) * 0x00800080u;
#pragma unroll
          for (int i = 0; i < 8; i++) {
            uint32_t o[4];
#pragma unroll
            for (int j = 0; j < 4; j++) {
              const uint32_t v = bmul2(x[4 * i + j], sc);
              asm("cvt.rn.f16x2.f32 %0, %1, %2;\n" : "=r"(o[j]) : "f"(bf_hi(v)), "f"(i + j == 0 ? h0 * bf_hi(sc) : bf_lo(v)));
            }
            sts128((dst + (i & 3) * 1024) ^ ((i >> 2) << 6), o[0], o[1], o[2], o[3]);
            load(nsrc, i);
          }
          if (n & 1) {
            const int f = min(max((int)e + eh - 129, 0), 254);
            if (lane < 2)
              asm volatile("st.async.weak.shared::cluster.mbarrier::complete_tx::bytes.b32 [%0], %2, [%1];\n"
                           ::"r"(mapa(sb + OFF_SC + rank * 32 + c * 4, lane)), "r"(mapa(bars + 8 * BAR_LAND, lane)), "r"(f << 7) : "memory");
          }
          eh = e;
        }
        fence_async_smem();
        __syncwarp();
        if (lane == 0) mbar_arrive(bars + 8 * BAR_UH);
        PROF(32);
      }
      if (hw < 3) {
        const uint32_t rb = mapa(bars, lane & 1);
        const uint32_t epoch = ld_relaxed(g_flag_o + 2 * cta + hw - 1) + 1;
        const bool own = hw - 1 == (rb2 & 1);
        nb_sync(NB_OREADY + hw - 1, 160);
        if (lane == 0) {
          asm volatile("cp.async.bulk.global.shared::cta.bulk_group [%0], [%1], %2;\n" ::"l"(g_o + (size_t)cta * 16384 + (hw - 1) * 8192),
                       "r"(sb + OFF_OP + (own ? 16384 : 0)), "r"(16384) : "memory");
          bulk_commit();
        }
        if (lane < 2) {
          mbar_arrive_cluster(rb + 8 * (BAR_EMPTY2 + 2));
          mbar_arrive_cluster(rb + 8 * (BAR_EMPTY2 + 3));
        }
        if (lane == 0) {
          bulk_wait0();
          if (own) mbar_expect_tx(bars + 8 * (BAR_FULL2 + 1), 16384);
          mbar_arrive_cluster(mapa(bars, own ? rank : rank ^ 1) + 8 * BAR_X);
          st_release(g_flag_o + 2 * cta + hw - 1, epoch);
          mbar_arrive(bars + 8 * BAR_REL);
        }
        __syncwarp();
        PROF(own ? 17 : 19);
      } else {
        if (MODE == 0) {
          mbar_wait_idle(bars + 8 * BAR_X, 0);
          if (elect_one())
            asm volatile("cp.async.bulk.shared::cluster.shared::cta.mbarrier::complete_tx::bytes [%0], [%1], %2, [%3];\n"
                         ::"r"(mapa(sb + OFF_OP, rank ^ 1)), "r"(sb + OFF_OP + 16384), "r"(16384),
                         "r"(mapa(bars + 8 * BAR_FULL2, rank ^ 1)) : "memory");
        }
        if (MODE == 0) {
          mbar_wait_idle(bars + 8 * BAR_DEAD, 0);
          if (elect_one()) {
            tma_load_3d(sb + g2_b(2), &tmWo, bars + 8 * (BAR_FULL2 + 2), 0, g2_k(hp, 2) * 64, cb2 * 2);
            tma_load_3d(sb + g2_b(3), &tmWo, bars + 8 * (BAR_FULL2 + 3), 0, g2_k(hp, 3) * 64, cb2 * 2);
          }
        }
        __syncwarp();
      }
      {
        const int c8 = (4 * (lr >> 1) + 2 * (lm & 1) + (lr & 1)) & 7;
        const bool own = (lr >> 2) == rank;
        const uint32_t ya = sb + (own ? y_slot(c8 & 1, c8 >> 1) : OFF_LAND + c8 * 2048);
        const uint32_t yx = ((lm >> 1) ^ lr) << 4;
        const int row = (lane >> 4) * 8 + ((lane >> 3) & 1) * 16 + ((lane >> 2) & 1);
        uint2* og = reinterpret_cast<uint2*>(p.out + (size_t)(rank * 1024 + row) * (2 * DM) + (chb & ~1) * 8 + (lane & 3) * 4);
        const uint32_t qa = sb + OFF_Q + (lane >> 4) * 512 + (lane & 15) * 8;
        mbar_wait(bars + 8 * BAR_Q, 0);
        mbar_wait_idle(bars + 8 * BAR_LAND, 0);
        PROF(33);
        const uint32_t t0 = clock();
        const uint4 s4 = lds128(sb + OFF_SC + (lane & 3) * 16);
        const uint32_t sc[2] = {s4.x | (s4.y << 16), s4.z | (s4.w << 16)};
        auto fin = [&](uint32_t q2, uint32_t y2, uint32_t s2) {
          float lo, hi;
          asm("{\n.reg .b16 l, h;\nmov.b32 {l, h}, %2;\ncvt.f32.f16 %0, l;\ncvt.f32.f16 %1, h;\n}\n" : "=f"(lo), "=f"(hi) : "r"(y2));
          return bmul2(q2, bmul2(pack_bf16(lo, hi), s2));
        };
#pragma unroll 1
        for (int j = hw - 1; j < 16; j += 3) {
          uint32_t y[4][4];
          uint2 q[8];
          while ((uint32_t)clock() - t0 < j * PACE) __nanosleep(40);
          const uint32_t qj = qa + j * 2048;
#pragma unroll
          for (int i = 0; i < 4; i++) ldsm4t(y[i], ya + j * 128 + (yx ^ (i << 5)));
#pragma unroll
          for (int i = 0; i < 8; i++) q[i] = lds64(qj + (i >> 2) * 1024 + (i & 3) * 128);
#pragma unroll
          for (int i = 0; i < 8; i++) {
            og[(size_t)(j * 64 + (i >> 2) * 32 + (i & 3) * 2) * (2 * DM / 4)] =
                make_uint2(fin(q[i].x, y[i >> 1][2 * (i & 1)], sc[0]), fin(q[i].y, y[i >> 1][2 * (i & 1) + 1], sc[1]));
            if (i < 7) asm volatile("nanosleep.u32 %0;\n" ::"r"(FINE) : "memory");
          }
        }
      }
      PROF(22);
    }
    cluster_sync_all();
  } else {
    asm volatile("setmaxnreg.inc.sync.aligned.u32 %0;\n" :: "n"(REG_MATH));
    if (warp == 0) PROF2(26);
    const int wg = warp >> 2;
    const int wtid = tid & 127;
    const bool signaller = (wtid == 0) || (wtid == 32);
    const uint32_t rbars = mapa(bars, wtid >> 5 & 1);

    if (halo_cta) {
      const uint32_t epoch = ld_relaxed(g_flag_h + blockIdx.x) + 1;
      float acc0[64], acc1[64];
      int s = 0, ph = 0;
#pragma unroll 1
      for (int kb = 0; kb < 16; kb++) {
        mbar_wait(bars + 8 * (BAR_FULLB + s), ph);
        const uint32_t st = sb + s * STGH;
        const uint64_t da = mkdesc(st, 16, 1024, 1);
        const uint64_t db = mkdesc(st + 8192 + wg * 32768, 8192, 1024, 1);
        wg_fence();
#pragma unroll
        for (int kk = 0; kk < 4; kk++) {
          wgmma_n128(acc0, da + 2 * kk, db + 128 * kk, kb + kk);
          wgmma_n128(acc1, da + 2 * kk, db + 1024 + 128 * kk, kb + kk);
        }
        wg_commit();
        wg_wait<0>();
        if (wtid == 0) mbar_arrive(bars + 8 * (BAR_EMPTYB + s));
        if (++s == 3) { s = 0; ph ^= 1; }
      }
      fence_regs(acc0);
      fence_regs(acc1);
      if ((warp & 3) != 3) {
#pragma unroll
        for (int hh = 0; hh < 2; hh++) {
          uint4* dst = g_halo + ((hh * 4 + (warp & 3) + 1) * 16 + blockIdx.x * 4) * 128 + wg * 64 + lane;
#pragma unroll
          for (int j = 0; j < 4; j++) {
            const int o = 16 * j + 2 * hh;
            dst[(j >> 1) * 128 + (j & 1) * 32] =
                make_uint4(pack_bf16(acc0[o], acc0[o + 1]), pack_bf16(acc0[o + 4], acc0[o + 5]),
                           pack_bf16(acc0[o + 8], acc0[o + 9]), pack_bf16(acc0[o + 12], acc0[o + 13]));
            dst[(2 + (j >> 1)) * 128 + (j & 1) * 32] =
                make_uint4(pack_bf16(acc1[o], acc1[o + 1]), pack_bf16(acc1[o + 4], acc1[o + 5]),
                           pack_bf16(acc1[o + 8], acc1[o + 9]), pack_bf16(acc1[o + 12], acc1[o + 13]));
          }
        }
      }
      nb_sync(NB_G1DONE, 256);
      if (tid == 0) st_release(g_flag_h + blockIdx.x, epoch);
      PROF(36);
      cluster_sync_all();
      return;
    }

    float acc[64];
    auto g2_step = [&](int s, int kb) {
      const uint64_t da = mkdesc(sb + g2_a(s) + wg * 8192, 16, 1024, 1);
      const uint64_t db = mkdesc(sb + g2_b(s), 8192, 1024, 1);
      wg_fence();
      wgmma_n128(acc, da, db, kb);
      wgmma_n128(acc, da + 2, db + 128, 1);
      wgmma_n128(acc, da + 4, db + 256, 1);
      wgmma_n128(acc, da + 6, db + 384, 1);
      wg_commit();
    };

    if (MODE != 2) {
    uint32_t a1[2][4], tw[16], d1[32];
    const uint32_t tb = sb + OFF_T + wtid * 16;
    const uint64_t dx = mkdesc(sb + OFF_U + wg * 4096, OFF_H - OFF_U, 1024, 1);
    auto s1 = [&](int it) {
      hmma_n128t<0>(d1, a1[0], dx + it * 512);
      hmma_n128t<1>(d1, a1[1], dx + it * 512 + 128);
      wg_commit();
    };
    auto ldtw = [&](int i) {
      const uint4 v = lds128(tb + T_TW + i * 2048);
      tw[4 * i] = v.x; tw[4 * i + 1] = v.y; tw[4 * i + 2] = v.z; tw[4 * i + 3] = v.w;
    };
    {
      float acc0[96], acc1[96];
      int sa = 0, pha = 0, sbb = 0, phb = 0;
      asm volatile("cp.async.wait_group 0;\n" ::: "memory");
      fence_async_smem();
      nb_sync(NB_FIRST, 256);
      if (tid == 0) {
        mbar_arrive(bars + 8 * BAR_FULLA);
        mbar_arrive(bars + 8 * BAR_FULLB);
      }
      PROF(0 + wg);
#pragma unroll 1
      for (int kb = 0; kb < 30; kb++) {
        if (!(kb & 1)) mbar_wait(bars + 8 * (BAR_FULLA + sa), pha);
        mbar_wait(bars + 8 * (BAR_FULLB + sbb), phb);
        if (kb == 0) PROF2(0 + wg);
        if (kb == 4 && wg == 0) PROF2(28);
        if (kb == 8 && wg == 0) PROF2(29);
        if (kb == 16 && wg == 0) PROF2(30);
        const uint64_t da = mkdesc(sb + sa * STG1A + wg * 16384 + (kb & 1) * 64, 16, 1024, 1);
        const uint64_t db = mkdesc(sb + OFF_1B + sbb * STG1B, 4096, 1024, 1);
        wg_fence();
        wgmma_n192(acc0, da, db, kb);
        wgmma_n192(acc1, da + 512, db, kb);
        wgmma_n192(acc0, da + 2, db + 128, 1);
        wgmma_n192(acc1, da + 514, db + 128, 1);
        wg_commit();
        wg_wait<1>();
        if (kb > 0) {
          if (wtid == 64) mbar_arrive(bars + 8 * (BAR_EMPTYB + (sbb == 0 ? NS1B - 1 : sbb - 1)));
          if (!(kb & 1) && signaller) mbar_arrive_cluster(rbars + 8 * (BAR_EMPTYA + (sa == 0 ? NS1A - 1 : sa - 1)));
        }
        if (++sbb == NS1B) { sbb = 0; phb ^= 1; }
        if ((kb & 1) && ++sa == NS1A) { sa = 0; pha ^= 1; }
      }
      const int blk0 = wg * 8 + (warp & 3);
      const int lr = lane & 7, lm = lane >> 3;
      const bool le0 = 2 * (lane & 3) <= (lane >> 2), le1 = 2 * (lane & 3) + 1 <= (lane >> 2);
      const uint32_t maskLE = (le0 ? 0x0000FFFFu : 0u) | (le1 ? 0xFFFF0000u : 0u);
      uint32_t k0[2][2][4], k1[2][2][4], qa[2][2][8];
      float l[2][2][4];
      {
        static_assert(15 % NS1A == 0 && 30 % NS1B == 0, "slots of the last k blocks");
        mbar_wait(bars + 8 * BAR_FULLA, 1);
        mbar_wait(bars + 8 * BAR_FULLB, 0);
        mbar_wait(bars + 8 * (BAR_FULLB + 1), 0);
        const uint64_t da = mkdesc(sb + wg * 16384, 16, 1024, 1);
        const uint64_t db = mkdesc(sb + OFF_1B, 4096, 1024, 1);
        wg_fence();
#pragma unroll
        for (int i = 0; i < 4; i++) wgmma_n192(acc0, da + 2 * i, db + (i >> 1) * (STG1B >> 4) + (i & 1) * 128, 1);
        wg_commit();
        wg_wait<1>();
        if (wtid == 64) mbar_arrive(bars + 8 * (BAR_EMPTYB + NS1B - 1));
#pragma unroll
        for (int i = 0; i < 2; i++) wgmma_n192(acc1, da + 512 + 2 * i, db + (i >> 1) * (STG1B >> 4) + (i & 1) * 128, 1);
        wg_commit();
        wg_wait<1>();
        fence_regs(acc0);
        attn_stage(sb, blk0, lane, acc0, k1[0]);
#pragma unroll
        for (int i = 2; i < 4; i++) wgmma_n192(acc1, da + 512 + 2 * i, db + (i >> 1) * (STG1B >> 4) + (i & 1) * 128, 1);
        wg_commit();
        attn_pack(acc0, qa[0], k0[0]);
        wg_wait<0>();
        fence_regs(acc1);
      }
      if (wtid == 64) mbar_arrive(bars + 8 * BAR_EMPTYB);
      PROF(2 + wg);
      attn_stage(sb, blk0 + 4, lane, acc1, k1[1]);
      __syncwarp();
      if (lane == 0) mbar_arrive(bars + 8 * BAR_STG);
      mbar_wait(bars + 8 * BAR_U, 0);
      attn_pack(acc1, qa[1], k0[1]);
      attn_own(k0[0], k1[0], le0, le1, qa[0], l[0]);
      attn_own(k0[1], k1[1], le0, le1, qa[1], l[1]);
      static_assert(OFF_L0 + 2048 == OFF_VP, "halo V rows");
      const uint32_t vl0 = sb + OFF_VP - 1024 + blk0 * 2048 + (lm >> 1) * 1024 + lr * 128 + (((lm & 1) ^ lr) << 4);
      const uint32_t vl[4] = {vl0, vl0 ^ 64, vl0 ^ 32, vl0 ^ 96};
      const uint32_t obase = sb + OFF_OP + (wg == (rb2 & 1) ? 16384 : 0) + ((warp & 3) * 16 + lr) * 128 + ((lm ^ lr) << 4);
      mbar_wait(bars + 8 * BAR_STG, 0);
      {
        uint32_t km[4][4], va[8][4], vb[8][4], pp[8];
        float x[8][2];
#pragma unroll
        for (int n = 0; n < 4; n++) {
          const int blk = blk0 + 4 * (n >> 1);
          to_arr(km[n], lds128(sb + (blk == 0 ? OFF_L0 : OFF_KH + (blk - 1) * 2048) + (n & 1) * 512 + lane * 16));
        }
#pragma unroll
        for (int n = 0; n < 8; n++) {
          const uint32_t o = ((n >> 1) & 1) * 8192 + (n >> 2) * 1024;
          ldsm4t(va[n], vl[n & 1] + o);
          ldsm4t(vb[n], vl[2 + (n & 1)] + o);
        }
        const bool first = blk0 == 0 && gidx == 0;
#pragma unroll
        for (int n = 0; n < 4; n++) {
          const uint32_t(&q)[8] = qa[n >> 1][n & 1];
          float sm[4];
          mma16816_z(sm, q[0], q[1], q[2], q[3], km[n][0], km[n][1]);
          mma16816(sm, q[4], q[5], q[6], q[7], km[n][2], km[n][3]);
          if (n < 2 && first) sm[0] = sm[1] = -1e9f / 0.17677669529663687f;
          x[n][0] = le0 ? l[n >> 1][n & 1][0] : sm[0];
          x[n][1] = le1 ? l[n >> 1][n & 1][1] : sm[1];
          x[4 + n][0] = l[n >> 1][n & 1][2];
          x[4 + n][1] = l[n >> 1][n & 1][3];
        }
        quad_softmax<8>(x, pp);
#pragma unroll
        for (int n = 7; n >= 0; n--)
          attn_pv((obase ^ ((n & 1) << 6)) + ((n >> 1) & 1) * 8192 + (n >> 2) * 1024, va[n], vb[n], pp[n], maskLE);
      }
      fence_async_smem();
      nb_arrive(NB_OREADY + wg, 160);
    }

    {
      const int w = warp & 3;
      uint32_t a4[8][4];
      uint32_t d4[8];
      PROF(34 + wg);
      const uint64_t dz = mkdesc(sb + OFF_U + wg * 4096, 512, 128, 0);
      const uint64_t db2 = mkdesc(sb + OFF_T + T_B2, 128, 256, 0);
      mbar_wait(bars + 8 * BAR_T, 0);
      mbar_wait(bars + 8 * BAR_UH, 0);
      to_arr(a1[0], lds128(tb + T_A1));
      to_arr(a1[1], lds128(tb + T_A1 + 2048));
      wg_fence();
      s1(0);
      ldtw(0);
      ldtw(1);
      const uint32_t za = sb + (w < 2 ? OFF_U : OFF_H) + wg * 4096 + (w & 1) * 2048 + lane * 16;
      const uint32_t yl = (wtid ^ (4 * rank + wg)) * 16;
      const uint32_t yown = mapa(sb, rank) + yl, yrem = mapa(sb + OFF_LAND + wg * 2048, rank ^ 1) + yl;
      const uint32_t yb[2] = {mapa(bars + 8 * BAR_LAND, 0), mapa(bars + 8 * BAR_LAND, 1)};
      wg_wait<0>();
      fence_regs(d1);
      nb_sync(NB_WG + wg, 128);
      auto s4 = [&](int it) {
        wg_fence();
#pragma unroll
        for (int ks = 0; ks < 8; ks++) {
          const uint64_t d = dz + (it & 1) * 512 + (ks & 3) * 64 + (ks >> 2) * ((OFF_H - OFF_U) >> 4);
          if (ks == 0) hmma_n32<0, 1>(d4, a4[ks], d);
          else hmma_n32<1, 1>(d4, a4[ks], d);
        }
        wg_commit();
      };
      auto e4 = [&](int it) {
        fence_regs(d4);
        const uint32_t o = (yown + y_slot(wg, it)) ^ ((it >> 1) << 5), m = (yrem + it * 4096) ^ ((it >> 1) << 5);
        if (it == 0) mbar_wait(bars + 8 * BAR_LFREE, 0);
        if (it == 3) mbar_wait(bars + 8 * (BAR_DEAD + 1), 0);
        st_async128(rank ? m : o, yb[0], d4[0], d4[1], d4[2], d4[3]);
        st_async128(rank ? o : m, yb[1], d4[4], d4[5], d4[6], d4[7]);
      };
      uint32_t a2[2][2][2][4], a3[2][2][4], d2[2][2][8], d3[2][8];
      auto s2a = [&]() {
        wg_fence();
#pragma unroll
        for (int c = 0; c < 4; c++) hmma_n32<0, 0>(d2[c & 1][c >> 1], a2[0][c & 1][c >> 1], db2 + (c >> 1) * 128);
      };
      auto s2b = [&]() {
        wg_fence();
#pragma unroll
        for (int c = 0; c < 4; c++) {
          hmma_n32<1, 0>(d2[c & 1][c >> 1], a2[1][c & 1][c >> 1], db2 + (c >> 1) * 128 + 64);
          if (c & 1) wg_commit();
        }
      };
      auto done = [&](int it) {
        if (it == 0) {
          if (signaller) mbar_arrive_cluster(rbars + 8 * BAR_LFREE);
        } else if (it >= 2 && wtid == 64) {
          mbar_arrive(bars + 8 * (BAR_DEAD + it - 2));
        }
        if (w == 0) PROF3(40 + 4 * wg + it);
      };
      fft_e1<0>(d1, tw, a2[0]);
      s2a();
      fft_e1<1>(d1, tw, a2[1]);
      s2b();
      s1(1);
      ldtw(2);
      ldtw(3);
#pragma unroll
      for (int i = 0; i < 8; i++) to_arr(a4[i], lds128(tb + T_A4 + i * 2048));
#pragma unroll
      for (int it = 0; it < 4; it++) {
        if (it == 0 || it == 3) wg_wait<2>(); else wg_wait<3>();
        fence_regs(d2[0][0]);
        fence_regs(d2[1][0]);
        fft_e2<0, 0>(d2[0][0], d2[1][0], a3[0]);
        fft_e2<0, 1>(d2[0][0], d2[1][0], a3[1]);
        if (it == 0 || it == 3) wg_wait<1>(); else wg_wait<2>();
        fence_regs(d2[0][1]);
        fence_regs(d2[1][1]);
        fft_e2<1, 0>(d2[0][1], d2[1][1], a3[0]);
        fft_e2<1, 1>(d2[0][1], d2[1][1], a3[1]);
        wg_fence();
        hmma_n32<0, 0>(d3[0], a3[0][0], db2);
        hmma_n32<0, 0>(d3[1], a3[0][1], db2);
        hmma_n32<1, 0>(d3[0], a3[1][0], db2 + 64);
        hmma_n32<1, 0>(d3[1], a3[1][1], db2 + 64);
        wg_commit();
        wg_wait<1>();
        if (it > 0) e4(it - 1);
        if (it < 3) {
          fence_regs(d1);
          fft_e1<0>(d1, tw, a2[0]);
        }
        wg_wait<0>();
        fence_regs(d3[0]);
        fence_regs(d3[1]);
        if (it < 3) s2a();
        fft_e3(d3, tw, za + (it & 1) * 8192);
        if (it < 3) {
          fft_e1<1>(d1, tw, a2[1]);
          s2b();
        }
        fence_async_smem();
        nb_sync(NB_WG + wg, 128);
        done(it);
        s4(it);
        if (it < 2) s1(it + 2);
      }
      if (PEEL && MODE == 0) {
        mbar_wait(bars + 8 * BAR_FULL2, 0);
        g2_step(0, 0);
        wg_wait<1>();
      } else {
        wg_wait<0>();
      }
      if (signaller) mbar_arrive_cluster(rbars + 8 * (BAR_EMPTY2 + 4));
      e4(3);
      if (PEEL && MODE == 0) {
        wg_wait<0>();
        if (signaller) mbar_arrive_cluster(rbars + 8 * BAR_EMPTY2);
      }
      PROF(6 + wg);
    }
    }

    if (MODE != 1) {
      int s = PEEL && MODE == 0, ph = 0;
#pragma unroll 1
      for (int kb = s; kb < STAG; kb++) {
        mbar_wait(bars + 8 * (BAR_FULL2 + s), ph);
        if (kb == 1) PROF(8 + wg);
        if (warp == 4) PROF2(40 + kb);
        g2_step(s, kb);
        wg_wait<0>();
        if (kb < 16 - NS2 && signaller) mbar_arrive_cluster(rbars + 8 * (BAR_EMPTY2 + s));
        if (++s == NS2) { s = 0; ph ^= 1; }
      }
      if (STAG < 16) {
        if (wg == LAST) nb_sync(NB_LEAD, 256);
#pragma unroll
        for (int kb = STAG; kb < 16; kb++) {
          mbar_wait(bars + 8 * (BAR_FULL2 + kb % NS2), (kb / NS2) & 1);
          g2_step(kb % NS2, 1);
        }
        if (wg != LAST) nb_arrive(NB_LEAD, 256);
      }
      wg_wait<0>();
      fence_regs(acc);
      PROF(10 + wg);
      const int lr = lane & 7, lm = lane >> 3;
      const uint32_t wbase = sb + warp * 2048;
      const uint32_t base = wbase + (lr + 8 * (lm & 1)) * 128;
#pragma unroll
      for (int j = 0; j < 16; j += 2) {
        const uint32_t a = base + (j >> 3) * 16384 + ((((j & 7) + (lm >> 1)) ^ lr) << 4);
        stsm4(a, pack_bf16(acc[4 * j], acc[4 * j + 1]), pack_bf16(acc[4 * j + 2], acc[4 * j + 3]),
              pack_bf16(acc[4 * j + 4], acc[4 * j + 5]), pack_bf16(acc[4 * j + 6], acc[4 * j + 7]));
      }
      __syncwarp();
      {
        const int rr = lane >> 4, ck = lane & 7, hf = (lane >> 3) & 1;
        uint4* og = reinterpret_cast<uint4*>(p.out + (size_t)(2 * ((rb2 & 7) * 128 + warp * 16 + rr) + (rb2 >> 3)) * (2 * DM) + DM + cb2 * 128 + hf * 64 + ck * 8);
        uint4 v[8];
#pragma unroll
        for (int i = 0; i < 8; i++) v[i] = lds128(wbase + hf * 16384 + (2 * i + rr) * 128 + ((ck ^ ((2 * i + rr) & 7)) << 4));
#pragma unroll
        for (int i = 0; i < 8; i++) og[(size_t)i * 4 * (2 * DM / 8)] = v[i];
      }
      PROF(12 + wg);
    }
    cluster_sync_all();
  }
}

typedef CUresult (*EncodeFn)(CUtensorMap*, CUtensorMapDataType, cuuint32_t, void*, const cuuint64_t*, const cuuint64_t*,
                             const cuuint32_t*, const cuuint32_t*, CUtensorMapInterleave, CUtensorMapSwizzle,
                             CUtensorMapL2promotion, CUtensorMapFloatOOBfill);

void make_map(EncodeFn enc, CUtensorMap* tm, const void* base, int rank, const cuuint64_t* dims, const cuuint64_t* strides,
              const cuuint32_t* box, CUtensorMapSwizzle swz) {
  cuuint32_t es[5] = {1, 1, 1, 1, 1};
  enc(tm, CU_TENSOR_MAP_DATA_TYPE_BFLOAT16, rank, const_cast<void*>(base), dims, strides, box, es,
      CU_TENSOR_MAP_INTERLEAVE_NONE, swz, CU_TENSOR_MAP_L2_PROMOTION_L2_256B, CU_TENSOR_MAP_FLOAT_OOB_FILL_NONE);
}

}

extern "C" void kernel_launch(void* const* d_in, const int* in_sizes, int n_in, void* d_out, int out_size) {
  static EncodeFn enc = nullptr;
  static bool coresident = true;
  if (!enc) {
    void* fn = nullptr;
    cudaDriverEntryPointQueryResult qr;
    cudaGetDriverEntryPoint("cuTensorMapEncodeTiled", &fn, cudaEnableDefault, &qr);
    enc = (EncodeFn)fn;
    cudaFuncSetAttribute(fused_kernel<0>, cudaFuncAttributeMaxDynamicSharedMemorySize, SMEM_BYTES);
    cudaFuncSetAttribute(fused_kernel<1>, cudaFuncAttributeMaxDynamicSharedMemorySize, SMEM_BYTES);
    cudaFuncSetAttribute(fused_kernel<2>, cudaFuncAttributeMaxDynamicSharedMemorySize, SMEM_BYTES);
    cudaLaunchConfig_t cfg = {};
    cfg.gridDim = dim3(NCTA);
    cfg.blockDim = dim3(NTHREADS);
    cfg.dynamicSmemBytes = SMEM_BYTES;
    cudaLaunchAttribute at;
    at.id = cudaLaunchAttributeClusterDimension;
    at.val.clusterDim.x = 2;
    at.val.clusterDim.y = 1;
    at.val.clusterDim.z = 1;
    cfg.attrs = &at;
    cfg.numAttrs = 1;
    int nclusters = 0;
    if (cudaOccupancyMaxActiveClusters(&nclusters, fused_kernel<0>, &cfg) == cudaSuccess) coresident = nclusters >= NCTA / 2;
    (void)cudaGetLastError();
  }
  CUtensorMap tmX, tmW, tmWo, tmQ, tmXh, tmWh;
  {
    cuuint64_t dims[3] = {1024, 2, 1024};
    cuuint64_t str[2] = {2048, 4096};
    cuuint32_t box[3] = {64, 1, 128};
    make_map(enc, &tmX, d_in[6], 3, dims, str, box, CU_TENSOR_MAP_SWIZZLE_128B);
  }
  {
    cuuint64_t dims[3] = {1024, 1024, 3};
    cuuint64_t str[2] = {6144, 2048};
    cuuint32_t box[3] = {64, 32, 3};
    make_map(enc, &tmW, d_in[7], 3, dims, str, box, CU_TENSOR_MAP_SWIZZLE_128B);
  }
  {
    cuuint64_t dims[3] = {64, 1024, 16};
    cuuint64_t str[2] = {2048, 128};
    cuuint32_t box[3] = {64, 64, 2};
    make_map(enc, &tmWo, d_in[8], 3, dims, str, box, CU_TENSOR_MAP_SWIZZLE_128B);
  }
  {
    cuuint64_t dims[5] = {1024, 2, 2, 8, 64};
    cuuint64_t str[4] = {2048, 16 * 2048, 2 * 2048, 32 * 2048};
    cuuint32_t box[5] = {16, 2, 2, 8, 4};
    make_map(enc, &tmQ, d_in[0], 5, dims, str, box, CU_TENSOR_MAP_SWIZZLE_NONE);
  }
  {
    cuuint64_t dims[4] = {1024, 256, 2, 4};
    cuuint64_t str[3] = {4096, 2048, 256 * 4096};
    cuuint32_t box[4] = {64, 8, 2, 4};
    make_map(enc, &tmXh, d_in[6], 4, dims, str, box, CU_TENSOR_MAP_SWIZZLE_128B);
  }
  {
    cuuint64_t dims[3] = {64, 1024, 48};
    cuuint64_t str[2] = {6144, 128};
    cuuint32_t box[3] = {64, 64, 4};
    make_map(enc, &tmWh, d_in[7], 3, dims, str, box, CU_TENSOR_MAP_SWIZZLE_128B);
  }
  Params p;
  p.q = (const __nv_bfloat16*)d_in[0];
  p.k = (const __nv_bfloat16*)d_in[1];
  p.v = (const __nv_bfloat16*)d_in[2];
  p.shift_k = (const __nv_bfloat16*)d_in[3];
  p.ssm_k = (const __nv_bfloat16*)d_in[4];
  p.ssm_D = (const __nv_bfloat16*)d_in[5];
  p.x = (const __nv_bfloat16*)d_in[6];
  p.w = (const __nv_bfloat16*)d_in[7];
  p.wo = (const __nv_bfloat16*)d_in[8];
  p.out = (__nv_bfloat16*)d_out;
  if (coresident) {
    fused_kernel<0><<<NCTA, NTHREADS, SMEM_BYTES>>>(p, tmX, tmW, tmWo, tmQ, tmXh, tmWh);
  } else {
    fused_kernel<0><<<4, NTHREADS, SMEM_BYTES>>>(p, tmX, tmW, tmWo, tmQ, tmXh, tmWh);
    fused_kernel<1><<<NCTA, NTHREADS, SMEM_BYTES>>>(p, tmX, tmW, tmWo, tmQ, tmXh, tmWh);
    fused_kernel<2><<<NCTA, NTHREADS, SMEM_BYTES>>>(p, tmX, tmW, tmWo, tmQ, tmXh, tmWh);
  }
}
```

```cpp
#include <cuda_runtime.h>
#include <cuda.h>
#include <cuda_bf16.h>
#include <stdint.h>

namespace {

constexpr int SEQ = 2048;
constexpr int DM = 1024;
constexpr int NCTA = 132;
constexpr int NTHREADS = 384;

constexpr int STG1A = 32768;
constexpr int NS1A = 3;
constexpr int STG1B = 12288;
constexpr int NS1B = 5;
constexpr int OFF_1B = NS1A * STG1A;
constexpr int STG2 = 32768;
constexpr int NS2 = 5;
constexpr int STGH = 73728;
constexpr int OFF_VP = 0;
constexpr int OFF_KH = 1 * STG2;
constexpr int OFF_OP = 2 * STG2;
constexpr int OFF_Q = 3 * STG2;
constexpr int T_A4 = 0, T_TW = 16384, T_B2 = 24576, T_A1 = 28672, T_END = 32768;
constexpr int OFF_U = 163840;
constexpr int OFF_H = OFF_U + 32768;
constexpr int OFF_T = OFF_U - T_END;
constexpr int OFF_LAND = 4 * STG2;
constexpr int OFF_BAR = OFF_H + 32768;
constexpr int OFF_SC = OFF_BAR + 512;
constexpr int OFF_L0 = -2048;
constexpr int SMEM_BYTES = 2048 + OFF_BAR + 1024;
static_assert(OFF_T + T_A1 == OFF_1B + NS1B * STG1B && OFF_T + T_TW == OFF_1B + 4 * STG1B && OFF_LAND == OFF_T + T_A4, "layout");
static_assert(3 * STGH <= OFF_BAR && SMEM_BYTES <= 232448, "smem");

constexpr int BAR_FULLA = 0;
constexpr int BAR_EMPTYA = 3;
constexpr int BAR_FULLB = 6;
constexpr int BAR_EMPTYB = 11;
constexpr int BAR_FULL2 = 16;
constexpr int BAR_EMPTY2 = 21;
constexpr int BAR_T = 26;
constexpr int BAR_UH = 27;
constexpr int BAR_LFREE = 28;
constexpr int BAR_LAND = 29;
constexpr int BAR_U = 30;
constexpr int BAR_Q = 31;
constexpr int BAR_STG = 32;
constexpr int BAR_DEAD = 33;
constexpr int BAR_X = 35;
constexpr int BAR_REL = 36;

constexpr int NB_G1DONE = 1;
constexpr int NB_OREADY = 2;
constexpr int NB_WG = 4;
constexpr int NB_HELP3 = 6;
constexpr int NB_FIRST = 7;
constexpr int NB_LEAD = 8;

#define PACE 390u
#define PF0 20
#define PEEL 1
#define IDLEW 1
#define LA0 3
#define LA1 4
#define STAG 12
#define LAST 0
#define FINE 40
#define POLL1 0
#define S1FIRST 0
#define REG_MATH 224
#define REG_HELP 56
constexpr int SPIN_LIMIT = 1 << 20;

__device__ __align__(1024) __nv_bfloat16 g_o[SEQ * DM];
__device__ uint32_t g_flag_o[256];
__device__ uint32_t g_flag_h[4];
__device__ uint4 g_halo[128 * 128];
__device__ __align__(128) const uint32_t g_tab[T_END / 4] = {
0x3c003c00,0x3bf13bff,0,0xafd6a648,0x3c003c00,0x3b993bce,0,0xb505b303,0x3c003c00,0x3af63b50,0,0xb7e3b67c,
0x3c003c00,0x3a0f3a8a,0,0xb93ab89b,0x3bc33bfe,0x3b773bfa,0xb3c6aa48,0xb5c2acb5,0x3a6d3b3b,0x389b3a4f,0xb8c4b6d7,0xba8ab8ec,
0x381d395f,0x26483505,0xbaddb9ed,0xbbffbb99,0x30b23564,0xb848b444,0xbbeabb88,0xbac2bbb6,0x3b0e3bf6,0x3a8a3bf1,0xb78bae46,0xb89bafd6,
0x34a53913,0xa6483732,0xbba8ba2f,0xbbffbb25,0xb78bae46,0xbac2b7e3,0xbb0ebbf6,0xb848baf6,0xbba8ba2f,0xbb50bbfa,0xb4a5b913,0x367cacb5,
0x39ed3bea,0x393a3be2,0xb95fb0b2,0xba0fb179,0xb56433c6,0xb8ec2648,0xbb88bbc3,0xba4fbbff,0xbbfeba6d,0xbb25bbce,0xaa48b8c4,0x3732b303,
0xb6d7badd,0x3444b67c,0x3b3b381d,0x3bb63b50,0x38723bd9,0x37323bce,0xbaa7b23e,0xbb25b303,0xbaa7b23e,0xbbb6b67c,0xb872bbd9,0xb444bb50,
0xb872bbd9,0xacb5ba8a,0x3aa7323e,0x3bfa389b,0x3aa7323e,0x3bf139cb,0x38723bd9,0xafd63984,0x35643bc3,0x33033bb6,0xbb88b3c6,0xbbceb444,
0xbbfeb8c4,0xbb77ba0f,0x2a48ba6d,0x35c2b93a,0x36d7b81d,0x3a8aafd6,0x3b3b3add,0x389b3bf1,0x395f3bea,0x26483b25,0xb9ed30b2,0xbbffb732,
0x2e463ba8,0xa6483b99,0xbbf6b4a5,0xbbffb505,0xba2fbb0e,0xb848bbb6,0x3913b78b,0x3ac2b444,0x3bf634a5,0x3b50393a,0x2e463ba8,0xb67c3a0f,
0xb913378b,0xbbe2afd6,0xba2fbb0e,0xb179bbf1,0xb0b23b88,0xb4443b77,0xbbeab564,0xbbb6b5c2,0xb3c6bbfe,0x2cb5bbe2,0x3bc3aa48,0x3bfa3179,
0x38c43b3b,0x2fd63bff,0xba6d36d7,0xbbf12648,0xbaddb95f,0xb505bbce,0x381db9ed,0x3b99b303,0xb61f3b64,0xb7e33b50,0xbb64b61f,0xbaf6b67c,
0x361fbb64,0x393aba8a,0x3b64361f,0x3a0f389b,0xb61f3b64,0xba4f3984,0xbb64b61f,0xb8ecb9cb,0x361fbb64,0x3b25b848,0x3b64361f,0x37323ac2,
0xb8c43b3b,0xb9843b25,0xba6db6d7,0xb9cbb732,0x3addb95f,0x3bceb7e3,0x381d39ed,0x33033af6,0xbbea3564,0xbb77acb5,0xb0b2bb88,0x35c2bbfa,
0x3bc32a48,0x389b38ec,0xb3c63bfe,0xba8a3a4f,0xba2f3b0e,0xbac23af6,0xb913b78b,0xb848b7e3,0x3bf6b4a5,0x3b50acb5,0xae463ba8,0xb67c3bfa,
0xb913b78b,0xb179ba4f,0x3a2fbb0e,0x3be2b8ec,0xae463ba8,0xb9cb3b99,0xbbf634a5,0xb984b505,0xbb3b3add,0xbb993ac2,0xb6d7b81d,0xb505b848,
0x39ed30b2,0x37e335c2,0xb95f3bea,0xbaf63b77,0x3564bbc3,0x3a0fbbe2,0x3b88b3c6,0x393a3179,0xbbfe38c4,0xba4f2648,0xaa48ba6d,0x38ecbbff,
0xbbd93aa7,0xbbfa3a8a,0xb23eb872,0xacb5b89b,0x323e3872,0xafd639cb,0xbbd93aa7,0xbbf13984,0x3bd9baa7,0x3b99b848,0x323e3872,0xb5053ac2,
0xb23eb872,0x37e3bb77,0x3bd9baa7,0x3af6b5c2,0xbbfe3a6d,0xbbe23a4f,0x2a48b8c4,0x3179b8ec,0xb6d73add,0xb9843b99,0xbb3b381d,0xb9cb3505,
0x395fb0b2,0x33033444,0xb9ed3bea,0xbbce3bb6,0x3b88bbc3,0x3b77b93a,0x356433c6,0xb5c23a0f,0xbba83a2f,0xbb503a0f,0x34a5b913,0x367cb93a,
0xbb0e3bf6,0xbbe23bf1,0xb78b2e46,0xb179afd6,0xb4a53913,0xb9cb3b25,0xbba83a2f,0xb9843732,0x378bae46,0xb30337e3,0xbb0e3bf6,0xbbce3af6,
0xbadd39ed,0xba4f39cb,0x381db95f,0x38ecb984,0xbbea3b88,0xbb253ac2,0x30b2b564,0x3732b848,0xbbc33bfe,0xbbb63b77,0xb3c62a48,0x3444b5c2,
0xba6d3b3b,0xbbfa3be2,0xb8c436d7,0x2cb5b179,0xb9a839a8,0xb8ec3984,0x39a8b9a8,0x3a4fb9cb,0xb9a839a8,0xb7323848,0x39a8b9a8,0x3b25bac2,
0xb9a839a8,0xb44435c2,0x39a8b9a8,0x3bb6bb77,0xb9a839a8,0xacb53179,0x39a8b9a8,0x3bfabbe2,0xb81d395f,0xb67c393a,0x3addb9ed,0x3b50ba0f,
0xb0b23564,0x31792fd6,0x3beabb88,0x3be2bbf1,0x33c6aa48,0x3984b732,0x3bc3bbfe,0x39cbbb25,0x38c4b6d7,0x3bcebaf6,0x3a6dbb3b,0x3303b7e3,
0xb4a53913,0xb17938ec,0x3ba8ba2f,0x3be2ba4f,0x378bae46,0x39cbb505,0x3b0ebbf6,0x3984bb99,0x3ba8ba2f,0x3bcebbb6,0x34a5b913,0xb303b444,
0x3b0ebbf6,0x35c2ba0f,0xb78b2e46,0xbb77393a,0xaa4838c4,0x2cb5389b,0x3bfeba6d,0x3bfaba8a,0x3b3bb81d,0x3bf1b984,0x36d7badd,0x2fd6b9cb,
0x39edbbea,0x3505bac2,0xb95f30b2,0xbb993848,0xb564b3c6,0xbaf635c2,0xbb883bc3,0xb7e33b77,0x323e3872,0x35053848,0x3bd9baa7,0x3b99bac2,
0x3bd9baa7,0x3af6bb77,0xb23eb872,0xb7e3b5c2,0xb23eb872,0xb93ab179,0xbbd93aa7,0xba0f3be2,0xbbd93aa7,0xb8ec3bff,0x323e3872,0x3a4fa648,
0x36d7381d,0x384837e3,0x3b3bbadd,0x3ac2baf6,0x395fbbea,0x367cbbfa,0xb9edb0b2,0xbb502cb5,0xbb8833c6,0xbbe238ec,0xb5643bc3,0x31793a4f,
0x2a483a6d,0x39843505,0x3bfeb8c4,0x39cbbb99,0x3913378b,0x39cb3732,0x3a2fbb0e,0x3984bb25,0x2e46bba8,0xb303baf6,0xbbf634a5,0xbbce37e3,
0xba2f3b0e,0xb5c23bfa,0x3913378b,0x3b772cb5,0x3bf6b4a5,0x3a8aba4f,0x2e46bba8,0xb89bb8ec,0x3a6d36d7,0x3af6367c,0x38c4bb3b,0x37e3bb50,
0xb81db9ed,0xba0fb89b,0xbadd395f,0xb93a3a8a,0x30b23b88,0x38ec39cb,0x3beab564,0x3a4fb984,0x33c6bbfe,0xb732bac2,0xbbc3aa48,0xbb253848,
0x3b64361f,0x3bb635c2,0x361fbb64,0x3444bb77,0xbb64b61f,0xbbfab179,0xb61f3b64,0xacb53be2,0x3b64361f,0x3bf1a648,0x361fbb64,0xafd6bbff,
0xbb64b61f,0xbb993303,0xb61f3b64,0x35053bce,0x3bea3564,0x3bff3505,0x30b2bb88,0x2648bb99,0xbbc32a48,0xbac23444,0x33c63bfe,0x38483bb6,
0x3a6db6d7,0x367cba0f,0xb8c4bb3b,0xbb50b93a,0xb81d39ed,0x31793bf1,0x3add395f,0x3be22fd6,0x3bf634a5,0x3bce3444,0xae46bba8,0xb303bbb6,
0xb913378b,0xb5c2393a,0x3a2f3b0e,0x3b773a0f,0xae46bba8,0xb89bbbf1,0xbbf6b4a5,0xba8a2fd6,0x3a2f3b0e,0x3bff3732,0x3913b78b,0xa648bb25,
0x3b8833c6,0x3b253303,0xb564bbc3,0xb732bbce,0xaa483a6d,0x34443b50,0x3bfe38c4,0x3bb6367c,0xbb3bbadd,0xbbfab89b,0xb6d7381d,0x2cb53a8a,
0x39edb0b2,0x2fd6b984,0xb95fbbea,0xbbf1b9cb,0x3aa7323e,0x3a0f3179,0xb872bbd9,0xb93abbe2,0x38723bd9,0x3a4f3bff,0x3aa7323e,0x38eca648,
0xbaa7b23e,0xb7323303,0x38723bd9,0x3b253bce,0xb872bbd9,0xbbb6bb50,0xbaa7b23e,0xb444367c,0x395f30b2,0x389b2fd6,0xb9edbbea,0xba8abbf1,
0x3b883bc3,0x3bff3b25,0x3564b3c6,0x2648b732,0x2a4838c4,0x38483af6,0x3bfe3a6d,0x3ac237e3,0xbb3bb81d,0xb67c2cb5,0x36d73add,0x3b503bfa,
0x378b2e46,0x35c22cb5,0xbb0ebbf6,0xbb77bbfa,0x3ba83a2f,0x3a8a38ec,0xb4a5b913,0xb89bba4f,0x3b0e3bf6,0x3bff3b99,0x378b2e46,0xa648b505,
0x34a53913,0x3ac23bb6,0x3ba83a2f,0x38483444,0x33c62a48,0x2fd62648,0xbbc3bbfe,0xbbf1bbff,0x38c436d7,0x35053303,0xba6dbb3b,0xbb99bbce,
0x3add39ed,0x37e3367c,0xb81db95f,0xbaf6bb50,0x3bea3b88,0x393a389b,0xb0b2b564,0xba0fba8a,0x3c003c00,0xbbf1bbff,0,0x2fd62648,
0x3c003c00,0xbb99bbce,0,0x35053303,0x3c003c00,0xbaf6bb50,0,0x37e3367c,0x3c003c00,0xba0fba8a,0,0x393a389b,
0x3bc33bfe,0xbb77bbfa,0xb3c6aa48,0x35c22cb5,0x3a6d3b3b,0xb89bba4f,0xb8c4b6d7,0x3a8a38ec,0x381d395f,0xa648b505,0xbaddb9ed,0x3bff3b99,
0x30b23564,0x38483444,0xbbeabb88,0x3ac23bb6,0x3b0e3bf6,0xba8abbf1,0xb78bae46,0x389b2fd6,0x34a53913,0x2648b732,0xbba8ba2f,0x3bff3b25,
0xb78bae46,0x3ac237e3,0xbb0ebbf6,0x38483af6,0xbba8ba2f,0x3b503bfa,0xb4a5b913,0xb67c2cb5,0x39ed3bea,0xb93abbe2,0xb95fb0b2,0x3a0f3179,
0xb56433c6,0x38eca648,0xbb88bbc3,0x3a4f3bff,0xbbfeba6d,0x3b253bce,0xaa48b8c4,0xb7323303,0xb6d7badd,0xb444367c,0x3b3b381d,0xbbb6bb50,
0x38723bd9,0xb732bbce,0xbaa7b23e,0x3b253303,0xbaa7b23e,0x3bb6367c,0xb872bbd9,0x34443b50,0xb872bbd9,0x2cb53a8a,0x3aa7323e,0xbbfab89b,
0x3aa7323e,0xbbf1b9cb,0x38723bd9,0x2fd6b984,0x35643bc3,0xb303bbb6,0xbb88b3c6,0x3bce3444,0xbbfeb8c4,0x3b773a0f,0x2a48ba6d,0xb5c2393a,
0x36d7b81d,0xba8a2fd6,0x3b3b3add,0xb89bbbf1,0x395f3bea,0xa648bb25,0xb9ed30b2,0x3bff3732,0x2e463ba8,0x2648bb99,0xbbf6b4a5,0x3bff3505,
0xba2fbb0e,0x38483bb6,0x3913b78b,0xbac23444,0x3bf634a5,0xbb50b93a,0x2e463ba8,0x367cba0f,0xb913378b,0x3be22fd6,0xba2fbb0e,0x31793bf1,
0xb0b23b88,0x3444bb77,0xbbeab564,0x3bb635c2,0xb3c6bbfe,0xacb53be2,0x3bc3aa48,0xbbfab179,0x38c43b3b,0xafd6bbff,0xba6d36d7,0x3bf1a648,
0xbaddb95f,0x35053bce,0x381db9ed,0xbb993303,0xb61f3b64,0x37e3bb50,0xbb64b61f,0x3af6367c,0x361fbb64,0xb93a3a8a,0x3b64361f,0xba0fb89b,
0xb61f3b64,0x3a4fb984,0xbb64b61f,0x38ec39cb,0x361fbb64,0xbb253848,0x3b64361f,0xb732bac2,0xb8c43b3b,0x3984bb25,0xba6db6d7,0x39cb3732,
0x3addb95f,0xbbce37e3,0x381d39ed,0xb303baf6,0xbbea3564,0x3b772cb5,0xb0b2bb88,0xb5c23bfa,0x3bc32a48,0xb89bb8ec,0xb3c63bfe,0x3a8aba4f,
0xba2f3b0e,0x3ac2baf6,0xb913b78b,0x384837e3,0x3bf6b4a5,0xbb502cb5,0xae463ba8,0x367cbbfa,0xb913b78b,0x31793a4f,0x3a2fbb0e,0xbbe238ec,
0xae463ba8,0x39cbbb99,0xbbf634a5,0x39843505,0xbb3b3add,0x3b99bac2,0xb6d7b81d,0x35053848,0x39ed30b2,0xb7e3b5c2,0xb95f3bea,0x3af6bb77,
0x3564bbc3,0xba0f3be2,0x3b88b3c6,0xb93ab179,0xbbfe38c4,0x3a4fa648,0xaa48ba6d,0xb8ec3bff,0xbbd93aa7,0x3bfaba8a,0xb23eb872,0x2cb5389b,
0x323e3872,0x2fd6b9cb,0xbbd93aa7,0x3bf1b984,0x3bd9baa7,0xbb993848,0x323e3872,0x3505bac2,0xb23eb872,0xb7e33b77,0x3bd9baa7,0xbaf635c2,
0xbbfe3a6d,0x3be2ba4f,0x2a48b8c4,0xb17938ec,0xb6d73add,0x3984bb99,0xbb3b381d,0x39cbb505,0x395fb0b2,0xb303b444,0xb9ed3bea,0x3bcebbb6,
0x3b88bbc3,0xbb77393a,0x356433c6,0x35c2ba0f,0xbba83a2f,0x3b50ba0f,0x34a5b913,0xb67c393a,0xbb0e3bf6,0x3be2bbf1,0xb78b2e46,0x31792fd6,
0xb4a53913,0x39cbbb25,0xbba83a2f,0x3984b732,0x378bae46,0x3303b7e3,0xbb0e3bf6,0x3bcebaf6,0xbadd39ed,0x3a4fb9cb,0x381db95f,0xb8ec3984,
0xbbea3b88,0x3b25bac2,0x30b2b564,0xb7323848,0xbbc33bfe,0x3bb6bb77,0xb3c62a48,0xb44435c2,0xba6d3b3b,0x3bfabbe2,0xb8c436d7,0xacb53179,
0xb9a839a8,0x38ecb984,0x39a8b9a8,0xba4f39cb,0xb9a839a8,0x3732b848,0x39a8b9a8,0xbb253ac2,0xb9a839a8,0x3444b5c2,0x39a8b9a8,0xbbb63b77,
0xb9a839a8,0x2cb5b179,0x39a8b9a8,0xbbfa3be2,0xb81d395f,0x367cb93a,0x3addb9ed,0xbb503a0f,0xb0b23564,0xb179afd6,0x3beabb88,0xbbe23bf1,
0x33c6aa48,0xb9843732,0x3bc3bbfe,0xb9cb3b25,0x38c4b6d7,0xbbce3af6,0x3a6dbb3b,0xb30337e3,0xb4a53913,0x3179b8ec,0x3ba8ba2f,0xbbe23a4f,
0x378bae46,0xb9cb3505,0x3b0ebbf6,0xb9843b99,0x3ba8ba2f,0xbbce3bb6,0x34a5b913,0x33033444,0x3b0ebbf6,0xb5c23a0f,0xb78b2e46,0x3b77b93a,
0xaa4838c4,0xacb5b89b,0x3bfeba6d,0xbbfa3a8a,0x3b3bb81d,0xbbf13984,0x36d7badd,0xafd639cb,0x39edbbea,0xb5053ac2,0xb95f30b2,0x3b99b848,
0xb564b3c6,0x3af6b5c2,0xbb883bc3,0x37e3bb77,0x323e3872,0xb505b848,0x3bd9baa7,0xbb993ac2,0x3bd9baa7,0xbaf63b77,0xb23eb872,0x37e335c2,
0xb23eb872,0x393a3179,0xbbd93aa7,0x3a0fbbe2,0xbbd93aa7,0x38ecbbff,0x323e3872,0xba4f2648,0x36d7381d,0xb848b7e3,0x3b3bbadd,0xbac23af6,
0x395fbbea,0xb67c3bfa,0xb9edb0b2,0x3b50acb5,0xbb8833c6,0x3be2b8ec,0xb5643bc3,0xb179ba4f,0x2a483a6d,0xb984b505,0x3bfeb8c4,0xb9cb3b99,
0x3913378b,0xb9cbb732,0x3a2fbb0e,0xb9843b25,0x2e46bba8,0x33033af6,0xbbf634a5,0x3bceb7e3,0xba2f3b0e,0x35c2bbfa,0x3913378b,0xbb77acb5,
0x3bf6b4a5,0xba8a3a4f,0x2e46bba8,0x389b38ec,0x3a6d36d7,0xbaf6b67c,0x38c4bb3b,0xb7e33b50,0xb81db9ed,0x3a0f389b,0xbadd395f,0x393aba8a,
0x30b23b88,0xb8ecb9cb,0x3beab564,0xba4f3984,0x33c6bbfe,0x37323ac2,0xbbc3aa48,0x3b25b848,0x3b64361f,0xbbb6b5c2,0x361fbb64,0xb4443b77,
0xbb64b61f,0x3bfa3179,0xb61f3b64,0x2cb5bbe2,0x3b64361f,0xbbf12648,0x361fbb64,0x2fd63bff,0xbb64b61f,0x3b99b303,0xb61f3b64,0xb505bbce,
0x3bea3564,0xbbffb505,0x30b2bb88,0xa6483b99,0xbbc32a48,0x3ac2b444,0x33c63bfe,0xb848bbb6,0x3a6db6d7,0xb67c3a0f,0xb8c4bb3b,0x3b50393a,
0xb81d39ed,0xb179bbf1,0x3add395f,0xbbe2afd6,0x3bf634a5,0xbbceb444,0xae46bba8,0x33033bb6,0xb913378b,0x35c2b93a,0x3a2f3b0e,0xbb77ba0f,
0xae46bba8,0x389b3bf1,0xbbf6b4a5,0x3a8aafd6,0x3a2f3b0e,0xbbffb732,0x3913b78b,0x26483b25,0x3b8833c6,0xbb25b303,0xb564bbc3,0x37323bce,
0xaa483a6d,0xb444bb50,0x3bfe38c4,0xbbb6b67c,0xbb3bbadd,0x3bfa389b,0xb6d7381d,0xacb5ba8a,0x39edb0b2,0xafd63984,0xb95fbbea,0x3bf139cb,
0x3aa7323e,0xba0fb179,0xb872bbd9,0x393a3be2,0x38723bd9,0xba4fbbff,0x3aa7323e,0xb8ec2648,0xbaa7b23e,0x3732b303,0x38723bd9,0xbb25bbce,
0xb872bbd9,0x3bb63b50,0xbaa7b23e,0x3444b67c,0x395f30b2,0xb89bafd6,0xb9edbbea,0x3a8a3bf1,0x3b883bc3,0xbbffbb25,0x3564b3c6,0xa6483732,
0x2a4838c4,0xb848baf6,0x3bfe3a6d,0xbac2b7e3,0xbb3bb81d,0x367cacb5,0x36d73add,0xbb50bbfa,0x378b2e46,0xb5c2acb5,0xbb0ebbf6,0x3b773bfa,
0x3ba83a2f,0xba8ab8ec,0xb4a5b913,0x389b3a4f,0x3b0e3bf6,0xbbffbb99,0x378b2e46,0x26483505,0x34a53913,0xbac2bbb6,0x3ba83a2f,0xb848b444,
0x33c62a48,0xafd6a648,0xbbc3bbfe,0x3bf13bff,0x38c436d7,0xb505b303,0xba6dbb3b,0x3b993bce,0x3add39ed,0xb7e3b67c,0xb81db95f,0x3af63b50,
0x3bea3b88,0xb93ab89b,0xb0b2b564,0x3a0f3a8a,0x3c003c00,0x38ec3984,0,0xba4fb9cb,0x3c003c00,0x37323848,0,0xbb25bac2,
0x3c003c00,0x344435c2,0,0xbbb6bb77,0x3c003c00,0x2cb53179,0,0xbbfabbe2,0xb3c6aa48,0xbb50ba0f,0xbbc3bbfe,0xb67cb93a,
0xb8c4b6d7,0xbbe2bbf1,0xba6dbb3b,0x3179afd6,0xbaddb9ed,0xb9cbbb25,0xb81db95f,0x39843732,0xbbeabb88,0xb303b7e3,0xb0b2b564,0x3bce3af6,
0xbb0ebbf6,0xb179b8ec,0x378b2e46,0x3be23a4f,0xb4a5b913,0x39cb3505,0x3ba83a2f,0x39843b99,0x378b2e46,0x3bce3bb6,0x3b0e3bf6,0xb3033444,
0x3ba83a2f,0x35c23a0f,0x34a53913,0xbb77b93a,0x395f30b2,0x3bfa3a8a,0x39ed3bea,0xacb5389b,0x3b883bc3,0x2fd639cb,0xb56433c6,0xbbf1b984,
0x2a4838c4,0xbb99b848,0xbbfeba6d,0xb505bac2,0xbb3bb81d,0xb7e3bb77,0xb6d7badd,0x3af635c2,0x38723bd9,0xb5053848,0xbaa7b23e,0xbb99bac2,
0xbaa7b23e,0xbaf6bb77,0xb872bbd9,0x37e3b5c2,0xb872bbd9,0x393ab179,0x3aa7323e,0x3a0f3be2,0x3aa7323e,0x38ec3bff,0x38723bd9,0xba4fa648,
0xbb88b3c6,0xbac2baf6,0xb564bbc3,0x3848b7e3,0x2a48ba6d,0x3b502cb5,0x3bfe38c4,0x367c3bfa,0x3b3b3add,0xb1793a4f,0xb6d7381d,0xbbe2b8ec,
0xb9ed30b2,0xb9cbbb99,0xb95fbbea,0x3984b505,0xae46bba8,0x39cbb732,0x3bf634a5,0x39843b25,0x3a2f3b0e,0xb3033af6,0xb913378b,0xbbceb7e3,
0xbbf6b4a5,0xb5c2bbfa,0xae46bba8,0x3b77acb5,0x3913b78b,0x3a8a3a4f,0x3a2f3b0e,0xb89b38ec,0x3bea3564,0x37e33b50,0xb0b23b88,0xbaf6367c,
0xbbc32a48,0xb93aba8a,0xb3c6bbfe,0x3a0fb89b,0x3a6db6d7,0x3a4f3984,0x38c43b3b,0xb8ec39cb,0xb81d39ed,0xbb25b848,0xbaddb95f,0x3732bac2,
0xb61f3b64,0xbbb635c2,0xbb64b61f,0xb444bb77,0x361fbb64,0x3bfab179,0x3b64361f,0x2cb53be2,0xb61f3b64,0xbbf1a648,0xbb64b61f,0x2fd6bbff,
0x361fbb64,0x3b993303,0x3b64361f,0xb5053bce,0xba6db6d7,0xa648bb99,0x38c4bb3b,0x3bffb505,0x381d39ed,0xb8483bb6,0xbadd395f,0xbac2b444,
0xb0b2bb88,0x3b50b93a,0x3beab564,0x367c3a0f,0xb3c63bfe,0xbbe22fd6,0xbbc3aa48,0x3179bbf1,0x3a2fbb0e,0x3bceb444,0x3913378b,0xb3033bb6,
0xbbf634a5,0xb5c2b93a,0x2e46bba8,0x3b77ba0f,0x3913378b,0xb89b3bf1,0xba2f3b0e,0xba8aafd6,0x2e46bba8,0x3bffb732,0x3bf6b4a5,0xa6483b25,
0x36d7381d,0xb7323bce,0xbb3b3add,0xbb253303,0x395fbbea,0x3bb6b67c,0x39ed30b2,0xb4443b50,0xbb8833c6,0x2cb5ba8a,0x3564bbc3,0x3bfab89b,
0x2a483a6d,0xbbf139cb,0xbbfe38c4,0xafd6b984,0xbbd93aa7,0xba0f3179,0xb23eb872,0x393abbe2,0x323e3872,0xba4f3bff,0xbbd93aa7,0xb8eca648,
0x3bd9baa7,0x37323303,0x323e3872,0xbb253bce,0xb23eb872,0x3bb6bb50,0x3bd9baa7,0x3444367c,0x2a48b8c4,0x3a8abbf1,0x3bfeba6d,0x389bafd6,
0xbb3b381d,0xa648b732,0x36d7badd,0x3bffbb25,0xb9ed3bea,0xbac237e3,0xb95f30b2,0x3848baf6,0x356433c6,0xbb503bfa,0xbb883bc3,0xb67cacb5,
0x3ba8ba2f,0x35c2acb5,0xb4a53913,0xbb773bfa,0x3b0ebbf6,0x3a8ab8ec,0x378bae46,0xb89b3a4f,0x34a5b913,0x3bffbb99,0x3ba8ba2f,0xa6483505,
0xb78b2e46,0x3ac2bbb6,0x3b0ebbf6,0x3848b444,0xb81d395f,0xbbf13bff,0xbadd39ed,0xafd62648,0xb0b23564,0xbb993bce,0xbbea3b88,0xb5053303,
0x33c6aa48,0xbaf63b50,0xbbc33bfe,0xb7e3367c,0x38c4b6d7,0xba0f3a8a,0xba6d3b3b,0xb93a389b,0xb9a839a8,0x2fd6a648,0x39a8b9a8,0x3bf1bbff,
0xb9a839a8,0x3505b303,0x39a8b9a8,0x3b99bbce,0xb9a839a8,0x37e3b67c,0x39a8b9a8,0x3af6bb50,0xb9a839a8,0x393ab89b,0x39a8b9a8,0x3a0fba8a,
0x3addb9ed,0x3b77bbfa,0x381db95f,0xb5c22cb5,0x3beabb88,0x389bba4f,0x30b2b564,0xba8a38ec,0x3bc3bbfe,0x2648b505,0xb3c62a48,0xbbff3b99,
0x3a6dbb3b,0xb8483444,0xb8c436d7,0xbac23bb6,0x34a5b913,0xb89b2fd6,0xbba83a2f,0xba8a3bf1,0xb78b2e46,0xbbff3b25,0xbb0e3bf6,0x26483732,
0xbba83a2f,0xb8483af6,0xb4a53913,0x3ac2b7e3,0xbb0e3bf6,0x367c2cb5,0x378bae46,0x3b50bbfa,0xbbfe3a6d,0xb93a3be2,0xaa4838c4,0x3a0fb179,
0xb6d73add,0x38ec2648,0x3b3bb81d,0x3a4fbbff,0x395fb0b2,0x3b25bbce,0x39edbbea,0xb732b303,0x3b88bbc3,0xb444b67c,0xb564b3c6,0xbbb63b50,
0x323e3872,0x3b25b303,0x3bd9baa7,0x3732bbce,0x3bd9baa7,0x3444bb50,0xb23eb872,0xbbb6367c,0xb23eb872,0xbbfa389b,0xbbd93aa7,0xacb53a8a,
0xbbd93aa7,0x2fd63984,0x323e3872,0x3bf1b9cb,0x3b3bbadd,0x3303bbb6,0xb6d7b81d,0xbbce3444,0xb9edb0b2,0xbb773a0f,0xb95f3bea,0x35c2393a,
0xb5643bc3,0x3a8a2fd6,0x3b88b3c6,0x389bbbf1,0x3bfeb8c4,0x2648bb25,0xaa48ba6d,0xbbff3732,0xb913b78b,0xbbff3505,0xba2f3b0e,0x26483b99,
0xae463ba8,0x3ac23444,0x3bf6b4a5,0x3848bbb6,0x3a2fbb0e,0xb67cba0f,0xb913b78b,0xbb50393a,0xbbf634a5,0xb1793bf1,0xae463ba8,0x3be2afd6,
0xb8c43b3b,0x34443b77,0x3a6d36d7,0x3bb6b5c2,0x3addb95f,0xacb5bbe2,0xb81db9ed,0xbbfa3179,0xbbea3564,0xafd63bff,0x30b23b88,0x3bf12648,
0x3bc32a48,0x3505bbce,0x33c6bbfe,0xbb99b303,0x3b64361f,0x3af6b67c,0x361fbb64,0xb7e3bb50,0xbb64b61f,0xba0f389b,0xb61f3b64,0x393a3a8a,
0x3b64361f,0x38ecb9cb,0x361fbb64,0xba4fb984,0xbb64b61f,0xb7323ac2,0xb61f3b64,0x3b253848,0x30b2bb88,0xb984bb25,0xbbeab564,0xb9cb3732,
0x33c63bfe,0x3bce37e3,0x3bc3aa48,0x3303baf6,0xb8c4bb3b,0xbb772cb5,0xba6d36d7,0x35c23bfa,0x3add395f,0x389bb8ec,0x381db9ed,0xba8aba4f,
0xbbf6b4a5,0xb84837e3,0x2e463ba8,0x3ac23af6,0x3913b78b,0xb67cbbfa,0xba2fbb0e,0xbb50acb5,0x2e463ba8,0x3be238ec,0x3bf634a5,0x3179ba4f,
0xba2fbb0e,0xb9843505,0xb913378b,0x39cb3b99,0x35643bc3,0x3b993ac2,0x3b8833c6,0x3505b848,0xbbfeb8c4,0xb7e335c2,0xaa483a6d,0x3af63b77,
0x36d7b81d,0xba0fbbe2,0xbb3bbadd,0xb93a3179,0x395f3bea,0x3a4f2648,0x39edb0b2,0xb8ecbbff,0x3aa7323e,0x2cb5b89b,0xb872bbd9,0xbbfaba8a,
0x38723bd9,0x3bf13984,0x3aa7323e,0xafd6b9cb,0xbaa7b23e,0x35053ac2,0x38723bd9,0x3b993848,0xb872bbd9,0xbaf6b5c2,0xbaa7b23e,0x37e33b77,
0xb9edbbea,0xbbe2ba4f,0xb95fb0b2,0x317938ec,0x3564b3c6,0xb984bb99,0xbb88bbc3,0xb9cbb505,0x3bfe3a6d,0x3303b444,0xaa48b8c4,0xbbcebbb6,
0x36d73add,0x3b77393a,0x3b3b381d,0xb5c2ba0f,0xb78bae46,0x367c393a,0x3b0e3bf6,0x3b503a0f,0xbba8ba2f,0xb1792fd6,0x34a53913,0x3be23bf1,
0xbb0ebbf6,0xb984b732,0xb78bae46,0x39cb3b25,0xb4a5b913,0xbbcebaf6,0xbba8ba2f,0x330337e3,0x3bc33bfe,0x3a4f39cb,0x33c62a48,0xb8ecb984,
0x3a6d3b3b,0x3b253ac2,0x38c436d7,0xb732b848,0x381d395f,0x3bb63b77,0x3add39ed,0xb444b5c2,0x30b23564,0x3bfa3be2,0x3bea3b88,0xacb5b179,
0x3c003c00,0xb8ecb984,0,0x3a4f39cb,0x3c003c00,0xb732b848,0,0x3b253ac2,0x3c003c00,0xb444b5c2,0,0x3bb63b77,
0x3c003c00,0xacb5b179,0,0x3bfa3be2,0xb3c6aa48,0x3b503a0f,0xbbc3bbfe,0x367c393a,0xb8c4b6d7,0x3be23bf1,0xba6dbb3b,0xb1792fd6,
0xbaddb9ed,0x39cb3b25,0xb81db95f,0xb984b732,0xbbeabb88,0x330337e3,0xb0b2b564,0xbbcebaf6,0xbb0ebbf6,0x317938ec,0x378b2e46,0xbbe2ba4f,
0xb4a5b913,0xb9cbb505,0x3ba83a2f,0xb984bb99,0x378b2e46,0xbbcebbb6,0x3b0e3bf6,0x3303b444,0x3ba83a2f,0xb5c2ba0f,0x34a53913,0x3b77393a,
0x395f30b2,0xbbfaba8a,0x39ed3bea,0x2cb5b89b,0x3b883bc3,0xafd6b9cb,0xb56433c6,0x3bf13984,0x2a4838c4,0x3b993848,0xbbfeba6d,0x35053ac2,
0xbb3bb81d,0x37e33b77,0xb6d7badd,0xbaf6b5c2,0x38723bd9,0x3505b848,0xbaa7b23e,0x3b993ac2,0xbaa7b23e,0x3af63b77,0xb872bbd9,0xb7e335c2,
0xb872bbd9,0xb93a3179,0x3aa7323e,0xba0fbbe2,0x3aa7323e,0xb8ecbbff,0x38723bd9,0x3a4f2648,0xbb88b3c6,0x3ac23af6,0xb564bbc3,0xb84837e3,
0x2a48ba6d,0xbb50acb5,0x3bfe38c4,0xb67cbbfa,0x3b3b3add,0x3179ba4f,0xb6d7381d,0x3be238ec,0xb9ed30b2,0x39cb3b99,0xb95fbbea,0xb9843505,
0xae46bba8,0xb9cb3732,0x3bf634a5,0xb984bb25,0x3a2f3b0e,0x3303baf6,0xb913378b,0x3bce37e3,0xbbf6b4a5,0x35c23bfa,0xae46bba8,0xbb772cb5,
0x3913b78b,0xba8aba4f,0x3a2f3b0e,0x389bb8ec,0x3bea3564,0xb7e3bb50,0xb0b23b88,0x3af6b67c,0xbbc32a48,0x393a3a8a,0xb3c6bbfe,0xba0f389b,
0x3a6db6d7,0xba4fb984,0x38c43b3b,0x38ecb9cb,0xb81d39ed,0x3b253848,0xbaddb95f,0xb7323ac2,0xb61f3b64,0x3bb6b5c2,0xbb64b61f,0x34443b77,
0x361fbb64,0xbbfa3179,0x3b64361f,0xacb5bbe2,0xb61f3b64,0x3bf12648,0xbb64b61f,0xafd63bff,0x361fbb64,0xbb99b303,0x3b64361f,0x3505bbce,
0xba6db6d7,0x26483b99,0x38c4bb3b,0xbbff3505,0x381d39ed,0x3848bbb6,0xbadd395f,0x3ac23444,0xb0b2bb88,0xbb50393a,0x3beab564,0xb67cba0f,
0xb3c63bfe,0x3be2afd6,0xbbc3aa48,0xb1793bf1,0x3a2fbb0e,0xbbce3444,0x3913378b,0x3303bbb6,0xbbf634a5,0x35c2393a,0x2e46bba8,0xbb773a0f,
0x3913378b,0x389bbbf1,0xba2f3b0e,0x3a8a2fd6,0x2e46bba8,0xbbff3732,0x3bf6b4a5,0x2648bb25,0x36d7381d,0x3732bbce,0xbb3b3add,0x3b25b303,
0x395fbbea,0xbbb6367c,0x39ed30b2,0x3444bb50,0xbb8833c6,0xacb53a8a,0x3564bbc3,0xbbfa389b,0x2a483a6d,0x3bf1b9cb,0xbbfe38c4,0x2fd63984,
0xbbd93aa7,0x3a0fb179,0xb23eb872,0xb93a3be2,0x323e3872,0x3a4fbbff,0xbbd93aa7,0x38ec2648,0x3bd9baa7,0xb732b303,0x323e3872,0x3b25bbce,
0xb23eb872,0xbbb63b50,0x3bd9baa7,0xb444b67c,0x2a48b8c4,0xba8a3bf1,0x3bfeba6d,0xb89b2fd6,0xbb3b381d,0x26483732,0x36d7badd,0xbbff3b25,
0xb9ed3bea,0x3ac2b7e3,0xb95f30b2,0xb8483af6,0x356433c6,0x3b50bbfa,0xbb883bc3,0x367c2cb5,0x3ba8ba2f,0xb5c22cb5,0xb4a53913,0x3b77bbfa,
0x3b0ebbf6,0xba8a38ec,0x378bae46,0x389bba4f,0x34a5b913,0xbbff3b99,0x3ba8ba2f,0x2648b505,0xb78b2e46,0xbac23bb6,0x3b0ebbf6,0xb8483444,
0xb81d395f,0x3bf1bbff,0xbadd39ed,0x2fd6a648,0xb0b23564,0x3b99bbce,0xbbea3b88,0x3505b303,0x33c6aa48,0x3af6bb50,0xbbc33bfe,0x37e3b67c,
0x38c4b6d7,0x3a0fba8a,0xba6d3b3b,0x393ab89b,0xb9a839a8,0xafd62648,0x39a8b9a8,0xbbf13bff,0xb9a839a8,0xb5053303,0x39a8b9a8,0xbb993bce,
0xb9a839a8,0xb7e3367c,0x39a8b9a8,0xbaf63b50,0xb9a839a8,0xb93a389b,0x39a8b9a8,0xba0f3a8a,0x3addb9ed,0xbb773bfa,0x381db95f,0x35c2acb5,
0x3beabb88,0xb89b3a4f,0x30b2b564,0x3a8ab8ec,0x3bc3bbfe,0xa6483505,0xb3c62a48,0x3bffbb99,0x3a6dbb3b,0x3848b444,0xb8c436d7,0x3ac2bbb6,
0x34a5b913,0x389bafd6,0xbba83a2f,0x3a8abbf1,0xb78b2e46,0x3bffbb25,0xbb0e3bf6,0xa648b732,0xbba83a2f,0x3848baf6,0xb4a53913,0xbac237e3,
0xbb0e3bf6,0xb67cacb5,0x378bae46,0xbb503bfa,0xbbfe3a6d,0x393abbe2,0xaa4838c4,0xba0f3179,0xb6d73add,0xb8eca648,0x3b3bb81d,0xba4f3bff,
0x395fb0b2,0xbb253bce,0x39edbbea,0x37323303,0x3b88bbc3,0x3444367c,0xb564b3c6,0x3bb6bb50,0x323e3872,0xbb253303,0x3bd9baa7,0xb7323bce,
0x3bd9baa7,0xb4443b50,0xb23eb872,0x3bb6b67c,0xb23eb872,0x3bfab89b,0xbbd93aa7,0x2cb5ba8a,0xbbd93aa7,0xafd6b984,0x323e3872,0xbbf139cb,
0x3b3bbadd,0xb3033bb6,0xb6d7b81d,0x3bceb444,0xb9edb0b2,0x3b77ba0f,0xb95f3bea,0xb5c2b93a,0xb5643bc3,0xba8aafd6,0x3b88b3c6,0xb89b3bf1,
0x3bfeb8c4,0xa6483b25,0xaa48ba6d,0x3bffb732,0xb913b78b,0x3bffb505,0xba2f3b0e,0xa648bb99,0xae463ba8,0xbac2b444,0x3bf6b4a5,0xb8483bb6,
0x3a2fbb0e,0x367c3a0f,0xb913b78b,0x3b50b93a,0xbbf634a5,0x3179bbf1,0xae463ba8,0xbbe22fd6,0xb8c43b3b,0xb444bb77,0x3a6d36d7,0xbbb635c2,
0x3addb95f,0x2cb53be2,0xb81db9ed,0x3bfab179,0xbbea3564,0x2fd6bbff,0x30b23b88,0xbbf1a648,0x3bc32a48,0xb5053bce,0x33c6bbfe,0x3b993303,
0x3b64361f,0xbaf6367c,0x361fbb64,0x37e33b50,0xbb64b61f,0x3a0fb89b,0xb61f3b64,0xb93aba8a,0x3b64361f,0xb8ec39cb,0x361fbb64,0x3a4f3984,
0xbb64b61f,0x3732bac2,0xb61f3b64,0xbb25b848,0x30b2bb88,0x39843b25,0xbbeab564,0x39cbb732,0x33c63bfe,0xbbceb7e3,0x3bc3aa48,0xb3033af6,
0xb8c4bb3b,0x3b77acb5,0xba6d36d7,0xb5c2bbfa,0x3add395f,0xb89b38ec,0x381db9ed,0x3a8a3a4f,0xbbf6b4a5,0x3848b7e3,0x2e463ba8,0xbac2baf6,
0x3913b78b,0x367c3bfa,0xba2fbb0e,0x3b502cb5,0x2e463ba8,0xbbe2b8ec,0x3bf634a5,0xb1793a4f,0xba2fbb0e,0x3984b505,0xb913378b,0xb9cbbb99,
0x35643bc3,0xbb99bac2,0x3b8833c6,0xb5053848,0xbbfeb8c4,0x37e3b5c2,0xaa483a6d,0xbaf6bb77,0x36d7b81d,0x3a0f3be2,0xbb3bbadd,0x393ab179,
0x395f3bea,0xba4fa648,0x39edb0b2,0x38ec3bff,0x3aa7323e,0xacb5389b,0xb872bbd9,0x3bfa3a8a,0x38723bd9,0xbbf1b984,0x3aa7323e,0x2fd639cb,
0xbaa7b23e,0xb505bac2,0x38723bd9,0xbb99b848,0xb872bbd9,0x3af635c2,0xbaa7b23e,0xb7e3bb77,0xb9edbbea,0x3be23a4f,0xb95fb0b2,0xb179b8ec,
0x3564b3c6,0x39843b99,0xbb88bbc3,0x39cb3505,0x3bfe3a6d,0xb3033444,0xaa48b8c4,0x3bce3bb6,0x36d73add,0xbb77b93a,0x3b3b381d,0x35c23a0f,
0xb78bae46,0xb67cb93a,0x3b0e3bf6,0xbb50ba0f,0xbba8ba2f,0x3179afd6,0x34a53913,0xbbe2bbf1,0xbb0ebbf6,0x39843732,0xb78bae46,0xb9cbbb25,
0xb4a5b913,0x3bce3af6,0xbba8ba2f,0xb303b7e3,0x3bc33bfe,0xba4fb9cb,0x33c62a48,0x38ec3984,0x3a6d3b3b,0xbb25bac2,0x38c436d7,0x37323848,
0x381d395f,0xbbb6bb77,0x3add39ed,0x344435c2,0x30b23564,0xbbfabbe2,0x3bea3b88,0x2cb53179,0x3c003c00,0xafd6a648,0,0xbbf1bbff,
0x3c003c00,0xb505b303,0,0xbb99bbce,0x3c003c00,0xb7e3b67c,0,0xbaf6bb50,0x3c003c00,0xb93ab89b,0,0xba0fba8a,
0xbbc3bbfe,0x35c22cb5,0x33c62a48,0x3b773bfa,0xba6dbb3b,0x3a8a38ec,0x38c436d7,0x389b3a4f,0xb81db95f,0x3bff3b99,0x3add39ed,0x26483505,
0xb0b2b564,0x3ac23bb6,0x3bea3b88,0xb848b444,0x3b0e3bf6,0xb89bafd6,0xb78bae46,0xba8abbf1,0x34a53913,0xbbffbb25,0xbba8ba2f,0x2648b732,
0xb78bae46,0xb848baf6,0xbb0ebbf6,0x3ac237e3,0xbba8ba2f,0x367cacb5,0xb4a5b913,0x3b503bfa,0xb9edbbea,0x3a0f3179,0x395f30b2,0x393a3be2,
0x3564b3c6,0x3a4f3bff,0x3b883bc3,0xb8ec2648,0x3bfe3a6d,0xb7323303,0x2a4838c4,0xbb25bbce,0x36d73add,0xbbb6bb50,0xbb3bb81d,0x3444b67c,
0x38723bd9,0xbb25b303,0xbaa7b23e,0xb732bbce,0xbaa7b23e,0xb444bb50,0xb872bbd9,0x3bb6367c,0xb872bbd9,0x3bfa389b,0x3aa7323e,0x2cb53a8a,
0x3aa7323e,0xafd63984,0x38723bd9,0xbbf1b9cb,0xb564bbc3,0x3bce3444,0x3b8833c6,0x33033bb6,0x3bfe38c4,0xb5c2393a,0xaa483a6d,0xbb77ba0f,
0xb6d7381d,0xb89bbbf1,0xbb3bbadd,0x3a8aafd6,0xb95fbbea,0x3bff3732,0x39edb0b2,0x26483b25,0x2e463ba8,0xbbffb505,0xbbf6b4a5,0x2648bb99,
0xba2fbb0e,0x3ac2b444,0x3913b78b,0x38483bb6,0x3bf634a5,0xb67c3a0f,0x2e463ba8,0xbb50b93a,0xb913378b,0xb179bbf1,0xba2fbb0e,0x3be22fd6,
0x30b2bb88,0x3bb635c2,0x3bea3564,0xb4443b77,0x33c63bfe,0xbbfab179,0xbbc32a48,0x2cb5bbe2,0xb8c4bb3b,0x3bf1a648,0x3a6db6d7,0x2fd63bff,
0x3add395f,0xbb993303,0xb81d39ed,0xb505bbce,0xb61f3b64,0xbaf6b67c,0xbb64b61f,0x37e3bb50,0x361fbb64,0x3a0f389b,0x3b64361f,0xb93a3a8a,
0xb61f3b64,0xb8ecb9cb,0xbb64b61f,0x3a4fb984,0x361fbb64,0x37323ac2,0x3b64361f,0xbb253848,0x38c4bb3b,0x39cb3732,0x3a6d36d7,0xb9843b25,
0xbadd395f,0xb303baf6,0xb81db9ed,0x3bceb7e3,0x3beab564,0xb5c23bfa,0x30b23b88,0xbb77acb5,0xbbc3aa48,0x3a8aba4f,0x33c6bbfe,0x389b38ec,
0xba2f3b0e,0xb848b7e3,0xb913b78b,0x3ac2baf6,0x3bf6b4a5,0xb67c3bfa,0xae463ba8,0xbb502cb5,0xb913b78b,0x3be2b8ec,0x3a2fbb0e,0x31793a4f,
0xae463ba8,0xb984b505,0xbbf634a5,0x39cbbb99,0x3b3bbadd,0x35053848,0x36d7381d,0xbb993ac2,0xb9edb0b2,0x3af6bb77,0x395fbbea,0x37e335c2,
0xb5643bc3,0xb93ab179,0xbb8833c6,0x3a0fbbe2,0x3bfeb8c4,0xb8ec3bff,0x2a483a6d,0xba4f2648,0xbbd93aa7,0xacb5b89b,0xb23eb872,0x3bfaba8a,
0x323e3872,0xbbf13984,0xbbd93aa7,0x2fd6b9cb,0x3bd9baa7,0xb5053ac2,0x323e3872,0xbb993848,0xb23eb872,0x3af6b5c2,0x3bd9baa7,0xb7e33b77,
0x3bfeba6d,0xb17938ec,0xaa4838c4,0xbbe23a4f,0x36d7badd,0x39cbb505,0x3b3bb81d,0xb9843b99,0xb95f30b2,0x3bcebbb6,0x39edbbea,0x33033444,
0xbb883bc3,0x35c2ba0f,0xb564b3c6,0x3b77b93a,0xbba83a2f,0x367cb93a,0x34a5b913,0x3b50ba0f,0xbb0e3bf6,0xb179afd6,0xb78b2e46,0x3be2bbf1,
0xb4a53913,0xb9843732,0xbba83a2f,0x39cbbb25,0x378bae46,0xbbce3af6,0xbb0e3bf6,0x3303b7e3,0x3addb9ed,0xb8ec3984,0xb81d395f,0xba4f39cb,
0x3beabb88,0xb7323848,0xb0b23564,0xbb253ac2,0x3bc3bbfe,0xb44435c2,0x33c6aa48,0xbbb63b77,0x3a6dbb3b,0xacb53179,0x38c4b6d7,0xbbfa3be2,
0xb9a839a8,0x3a4fb9cb,0x39a8b9a8,0x38ecb984,0xb9a839a8,0x3b25bac2,0x39a8b9a8,0x3732b848,0xb9a839a8,0x3bb6bb77,0x39a8b9a8,0x3444b5c2,
0xb9a839a8,0x3bfabbe2,0x39a8b9a8,0x2cb5b179,0x381db95f,0xbb503a0f,0xbadd39ed,0xb67c393a,0x30b2b564,0xbbe23bf1,0xbbea3b88,0x31792fd6,
0xb3c62a48,0xb9cb3b25,0xbbc33bfe,0x3984b732,0xb8c436d7,0xb30337e3,0xba6d3b3b,0x3bcebaf6,0xb4a53913,0x3be2ba4f,0x3ba8ba2f,0x3179b8ec,
0x378bae46,0x3984bb99,0x3b0ebbf6,0xb9cb3505,0x3ba8ba2f,0xb303b444,0x34a5b913,0xbbce3bb6,0x3b0ebbf6,0xbb77393a,0xb78b2e46,0xb5c23a0f,
0x2a48b8c4,0xbbfa3a8a,0xbbfe3a6d,0x2cb5389b,0xbb3b381d,0xafd639cb,0xb6d73add,0x3bf1b984,0xb9ed3bea,0x3b99b848,0x395fb0b2,0x3505bac2,
0x356433c6,0x37e3bb77,0x3b88bbc3,0xbaf635c2,0x323e3872,0x3b99bac2,0x3bd9baa7,0xb505b848,0x3bd9baa7,0xb7e3b5c2,0xb23eb872,0xbaf63b77,
0xb23eb872,0xba0f3be2,0xbbd93aa7,0x393a3179,0xbbd93aa7,0x3a4fa648,0x323e3872,0x38ecbbff,0xb6d7b81d,0xbac23af6,0xbb3b3add,0x384837e3,
0xb95f3bea,0x3b50acb5,0x39ed30b2,0x367cbbfa,0x3b88b3c6,0xb179ba4f,0x3564bbc3,0xbbe238ec,0xaa48ba6d,0xb9cb3b99,0xbbfe38c4,0x39843505,
0x3913378b,0x3984bb25,0x3a2fbb0e,0xb9cbb732,0x2e46bba8,0xbbce37e3,0xbbf634a5,0x33033af6,0xba2f3b0e,0x3b772cb5,0x3913378b,0x35c2bbfa,
0x3bf6b4a5,0xb89bb8ec,0x2e46bba8,0xba8a3a4f,0xba6db6d7,0xb7e33b50,0xb8c43b3b,0x3af6367c,0x381d39ed,0x393aba8a,0x3addb95f,0xba0fb89b,
0xb0b2bb88,0xba4f3984,0xbbea3564,0x38ec39cb,0xb3c63bfe,0x3b25b848,0x3bc32a48,0xb732bac2,0x3b64361f,0x3444bb77,0x361fbb64,0xbbb6b5c2,
0xbb64b61f,0xacb53be2,0xb61f3b64,0x3bfa3179,0x3b64361f,0xafd6bbff,0x361fbb64,0xbbf12648,0xbb64b61f,0x35053bce,0xb61f3b64,0x3b99b303,
0xbbeab564,0xa6483b99,0xb0b23b88,0x3bff3505,0x3bc3aa48,0xb848bbb6,0xb3c6bbfe,0xbac23444,0xba6d36d7,0x3b50393a,0x38c43b3b,0x367cba0f,
0x381db9ed,0xbbe2afd6,0xbaddb95f,0x31793bf1,0x3bf634a5,0xb303bbb6,0xae46bba8,0xbbceb444,0xb913378b,0x3b773a0f,0x3a2f3b0e,0x35c2b93a,
0xae46bba8,0xba8a2fd6,0xbbf6b4a5,0x389b3bf1,0x3a2f3b0e,0xa648bb25,0x3913b78b,0xbbffb732,0xbb88b3c6,0x37323bce,0x35643bc3,0x3b253303,
0x2a48ba6d,0xbbb6b67c,0xbbfeb8c4,0x34443b50,0x3b3b3add,0xacb5ba8a,0x36d7b81d,0xbbfab89b,0xb9ed30b2,0x3bf139cb,0x395f3bea,0x2fd6b984,
0x3aa7323e,0xb93abbe2,0xb872bbd9,0xba0fb179,0x38723bd9,0x38eca648,0x3aa7323e,0xba4fbbff,0xbaa7b23e,0x3b253bce,0x38723bd9,0x3732b303,
0xb872bbd9,0xb444367c,0xbaa7b23e,0x3bb63b50,0xb95fb0b2,0x3a8a3bf1,0x39ed3bea,0x389b2fd6,0xbb88bbc3,0xa6483732,0xb56433c6,0x3bff3b25,
0xaa48b8c4,0xbac2b7e3,0xbbfeba6d,0x38483af6,0x3b3b381d,0xbb50bbfa,0xb6d7badd,0xb67c2cb5,0x378b2e46,0xbb77bbfa,0xbb0ebbf6,0xb5c2acb5,
0x3ba83a2f,0xb89bba4f,0xb4a5b913,0xba8ab8ec,0x3b0e3bf6,0xa648b505,0x378b2e46,0xbbffbb99,0x34a53913,0x38483444,0x3ba83a2f,0xbac2bbb6,
0xb3c6aa48,0x3bf13bff,0x3bc33bfe,0x2fd62648,0xb8c4b6d7,0x3b993bce,0x3a6d3b3b,0x35053303,0xbaddb9ed,0x3af63b50,0x381d395f,0x37e3367c,
0xbbeabb88,0x3a0f3a8a,0x30b23564,0x393a389b,0x3c003c00,0x2fd62648,0,0x3bf13bff,0x3c003c00,0x35053303,0,0x3b993bce,
0x3c003c00,0x37e3367c,0,0x3af63b50,0x3c003c00,0x393a389b,0,0x3a0f3a8a,0xbbc3bbfe,0xb5c2acb5,0x33c62a48,0xbb77bbfa,
0xba6dbb3b,0xba8ab8ec,0x38c436d7,0xb89bba4f,0xb81db95f,0xbbffbb99,0x3add39ed,0xa648b505,0xb0b2b564,0xbac2bbb6,0x3bea3b88,0x38483444,
0x3b0e3bf6,0x389b2fd6,0xb78bae46,0x3a8a3bf1,0x34a53913,0x3bff3b25,0xbba8ba2f,0xa6483732,0xb78bae46,0x38483af6,0xbb0ebbf6,0xbac2b7e3,
0xbba8ba2f,0xb67c2cb5,0xb4a5b913,0xbb50bbfa,0xb9edbbea,0xba0fb179,0x395f30b2,0xb93abbe2,0x3564b3c6,0xba4fbbff,0x3b883bc3,0x38eca648,
0x3bfe3a6d,0x3732b303,0x2a4838c4,0x3b253bce,0x36d73add,0x3bb63b50,0xbb3bb81d,0xb444367c,0x38723bd9,0x3b253303,0xbaa7b23e,0x37323bce,
0xbaa7b23e,0x34443b50,0xb872bbd9,0xbbb6b67c,0xb872bbd9,0xbbfab89b,0x3aa7323e,0xacb5ba8a,0x3aa7323e,0x2fd6b984,0x38723bd9,0x3bf139cb,
0xb564bbc3,0xbbceb444,0x3b8833c6,0xb303bbb6,0x3bfe38c4,0x35c2b93a,0xaa483a6d,0x3b773a0f,0xb6d7381d,0x389b3bf1,0xbb3bbadd,0xba8a2fd6,
0xb95fbbea,0xbbffb732,0x39edb0b2,0xa648bb25,0x2e463ba8,0x3bff3505,0xbbf6b4a5,0xa6483b99,0xba2fbb0e,0xbac23444,0x3913b78b,0xb848bbb6,
0x3bf634a5,0x367cba0f,0x2e463ba8,0x3b50393a,0xb913378b,0x31793bf1,0xba2fbb0e,0xbbe2afd6,0x30b2bb88,0xbbb6b5c2,0x3bea3564,0x3444bb77,
0x33c63bfe,0x3bfa3179,0xbbc32a48,0xacb53be2,0xb8c4bb3b,0xbbf12648,0x3a6db6d7,0xafd6bbff,0x3add395f,0x3b99b303,0xb81d39ed,0x35053bce,
0xb61f3b64,0x3af6367c,0xbb64b61f,0xb7e33b50,0x361fbb64,0xba0fb89b,0x3b64361f,0x393aba8a,0xb61f3b64,0x38ec39cb,0xbb64b61f,0xba4f3984,
0x361fbb64,0xb732bac2,0x3b64361f,0x3b25b848,0x38c4bb3b,0xb9cbb732,0x3a6d36d7,0x3984bb25,0xbadd395f,0x33033af6,0xb81db9ed,0xbbce37e3,
0x3beab564,0x35c2bbfa,0x30b23b88,0x3b772cb5,0xbbc3aa48,0xba8a3a4f,0x33c6bbfe,0xb89bb8ec,0xba2f3b0e,0x384837e3,0xb913b78b,0xbac23af6,
0x3bf6b4a5,0x367cbbfa,0xae463ba8,0x3b50acb5,0xb913b78b,0xbbe238ec,0x3a2fbb0e,0xb179ba4f,0xae463ba8,0x39843505,0xbbf634a5,0xb9cb3b99,
0x3b3bbadd,0xb505b848,0x36d7381d,0x3b99bac2,0xb9edb0b2,0xbaf63b77,0x395fbbea,0xb7e3b5c2,0xb5643bc3,0x393a3179,0xbb8833c6,0xba0f3be2,
0x3bfeb8c4,0x38ecbbff,0x2a483a6d,0x3a4fa648,0xbbd93aa7,0x2cb5389b,0xb23eb872,0xbbfa3a8a,0x323e3872,0x3bf1b984,0xbbd93aa7,0xafd639cb,
0x3bd9baa7,0x3505bac2,0x323e3872,0x3b99b848,0xb23eb872,0xbaf635c2,0x3bd9baa7,0x37e3bb77,0x3bfeba6d,0x3179b8ec,0xaa4838c4,0x3be2ba4f,
0x36d7badd,0xb9cb3505,0x3b3bb81d,0x3984bb99,0xb95f30b2,0xbbce3bb6,0x39edbbea,0xb303b444,0xbb883bc3,0xb5c23a0f,0xb564b3c6,0xbb77393a,
0xbba83a2f,0xb67c393a,0x34a5b913,0xbb503a0f,0xbb0e3bf6,0x31792fd6,0xb78b2e46,0xbbe23bf1,0xb4a53913,0x3984b732,0xbba83a2f,0xb9cb3b25,
0x378bae46,0x3bcebaf6,0xbb0e3bf6,0xb30337e3,0x3addb9ed,0x38ecb984,0xb81d395f,0x3a4fb9cb,0x3beabb88,0x3732b848,0xb0b23564,0x3b25bac2,
0x3bc3bbfe,0x3444b5c2,0x33c6aa48,0x3bb6bb77,0x3a6dbb3b,0x2cb5b179,0x38c4b6d7,0x3bfabbe2,0xb9a839a8,0xba4f39cb,0x39a8b9a8,0xb8ec3984,
0xb9a839a8,0xbb253ac2,0x39a8b9a8,0xb7323848,0xb9a839a8,0xbbb63b77,0x39a8b9a8,0xb44435c2,0xb9a839a8,0xbbfa3be2,0x39a8b9a8,0xacb53179,
0x381db95f,0x3b50ba0f,0xbadd39ed,0x367cb93a,0x30b2b564,0x3be2bbf1,0xbbea3b88,0xb179afd6,0xb3c62a48,0x39cbbb25,0xbbc33bfe,0xb9843732,
0xb8c436d7,0x3303b7e3,0xba6d3b3b,0xbbce3af6,0xb4a53913,0xbbe23a4f,0x3ba8ba2f,0xb17938ec,0x378bae46,0xb9843b99,0x3b0ebbf6,0x39cbb505,
0x3ba8ba2f,0x33033444,0x34a5b913,0x3bcebbb6,0x3b0ebbf6,0x3b77b93a,0xb78b2e46,0x35c2ba0f,0x2a48b8c4,0x3bfaba8a,0xbbfe3a6d,0xacb5b89b,
0xbb3b381d,0x2fd6b9cb,0xb6d73add,0xbbf13984,0xb9ed3bea,0xbb993848,0x395fb0b2,0xb5053ac2,0x356433c6,0xb7e33b77,0x3b88bbc3,0x3af6b5c2,
0x323e3872,0xbb993ac2,0x3bd9baa7,0x35053848,0x3bd9baa7,0x37e335c2,0xb23eb872,0x3af6bb77,0xb23eb872,0x3a0fbbe2,0xbbd93aa7,0xb93ab179,
0xbbd93aa7,0xba4f2648,0x323e3872,0xb8ec3bff,0xb6d7b81d,0x3ac2baf6,0xbb3b3add,0xb848b7e3,0xb95f3bea,0xbb502cb5,0x39ed30b2,0xb67c3bfa,
0x3b88b3c6,0x31793a4f,0x3564bbc3,0x3be2b8ec,0xaa48ba6d,0x39cbbb99,0xbbfe38c4,0xb984b505,0x3913378b,0xb9843b25,0x3a2fbb0e,0x39cb3732,
0x2e46bba8,0x3bceb7e3,0xbbf634a5,0xb303baf6,0xba2f3b0e,0xbb77acb5,0x3913378b,0xb5c23bfa,0x3bf6b4a5,0x389b38ec,0x2e46bba8,0x3a8aba4f,
0xba6db6d7,0x37e3bb50,0xb8c43b3b,0xbaf6b67c,0x381d39ed,0xb93a3a8a,0x3addb95f,0x3a0f389b,0xb0b2bb88,0x3a4fb984,0xbbea3564,0xb8ecb9cb,
0xb3c63bfe,0xbb253848,0x3bc32a48,0x37323ac2,0x3b64361f,0xb4443b77,0x361fbb64,0x3bb635c2,0xbb64b61f,0x2cb5bbe2,0xb61f3b64,0xbbfab179,
0x3b64361f,0x2fd63bff,0x361fbb64,0x3bf1a648,0xbb64b61f,0xb505bbce,0xb61f3b64,0xbb993303,0xbbeab564,0x2648bb99,0xb0b23b88,0xbbffb505,
0x3bc3aa48,0x38483bb6,0xb3c6bbfe,0x3ac2b444,0xba6d36d7,0xbb50b93a,0x38c43b3b,0xb67c3a0f,0x381db9ed,0x3be22fd6,0xbaddb95f,0xb179bbf1,
0x3bf634a5,0x33033bb6,0xae46bba8,0x3bce3444,0xb913378b,0xbb77ba0f,0x3a2f3b0e,0xb5c2393a,0xae46bba8,0x3a8aafd6,0xbbf6b4a5,0xb89bbbf1,
0x3a2f3b0e,0x26483b25,0x3913b78b,0x3bff3732,0xbb88b3c6,0xb732bbce,0x35643bc3,0xbb25b303,0x2a48ba6d,0x3bb6367c,0xbbfeb8c4,0xb444bb50,
0x3b3b3add,0x2cb53a8a,0x36d7b81d,0x3bfa389b,0xb9ed30b2,0xbbf1b9cb,0x395f3bea,0xafd63984,0x3aa7323e,0x393a3be2,0xb872bbd9,0x3a0f3179,
0x38723bd9,0xb8ec2648,0x3aa7323e,0x3a4f3bff,0xbaa7b23e,0xbb25bbce,0x38723bd9,0xb7323303,0xb872bbd9,0x3444b67c,0xbaa7b23e,0xbbb6bb50,
0xb95fb0b2,0xba8abbf1,0x39ed3bea,0xb89bafd6,0xbb88bbc3,0x2648b732,0xb56433c6,0xbbffbb25,0xaa48b8c4,0x3ac237e3,0xbbfeba6d,0xb848baf6,
0x3b3b381d,0x3b503bfa,0xb6d7badd,0x367cacb5,0x378b2e46,0x3b773bfa,0xbb0ebbf6,0x35c22cb5,0x3ba83a2f,0x389b3a4f,0xb4a5b913,0x3a8a38ec,
0x3b0e3bf6,0x26483505,0x378b2e46,0x3bff3b99,0x34a53913,0xb848b444,0x3ba83a2f,0x3ac23bb6,0xb3c6aa48,0xbbf1bbff,0x3bc33bfe,0xafd6a648,
0xb8c4b6d7,0xbb99bbce,0x3a6d3b3b,0xb505b303,0xbaddb9ed,0xbaf6bb50,0x381d395f,0xb7e3b67c,0xbbeabb88,0xba0fba8a,0x30b23564,0xb93ab89b,
0x3c003c00,0xba4fb9cb,0,0xb8ecb984,0x3c003c00,0xbb25bac2,0,0xb732b848,0x3c003c00,0xbbb6bb77,0,0xb444b5c2,
0x3c003c00,0xbbfabbe2,0,0xacb5b179,0x33c62a48,0x367c393a,0x3bc33bfe,0xbb50ba0f,0x38c436d7,0xb1792fd6,0x3a6d3b3b,0xbbe2bbf1,
0x3add39ed,0xb984b732,0x381d395f,0xb9cbbb25,0x3bea3b88,0xbbcebaf6,0x30b23564,0xb303b7e3,0xbb0ebbf6,0x3be23a4f,0x378b2e46,0x317938ec,
0xb4a5b913,0x39843b99,0x3ba83a2f,0xb9cbb505,0x378b2e46,0xb3033444,0x3b0e3bf6,0xbbcebbb6,0x3ba83a2f,0xbb77b93a,0x34a53913,0xb5c2ba0f,
0xb95fb0b2,0x2cb5b89b,0xb9edbbea,0x3bfa3a8a,0xbb88bbc3,0x3bf13984,0x3564b3c6,0x2fd639cb,0xaa48b8c4,0x35053ac2,0x3bfe3a6d,0xbb99b848,
0x3b3b381d,0xbaf6b5c2,0x36d73add,0xb7e3bb77,0x38723bd9,0xbb99bac2,0xbaa7b23e,0x3505b848,0xbaa7b23e,0x37e3b5c2,0xb872bbd9,0x3af63b77,
0xb872bbd9,0x3a0f3be2,0x3aa7323e,0xb93a3179,0x3aa7323e,0xba4fa648,0x38723bd9,0xb8ecbbff,0x3b8833c6,0xb84837e3,0x35643bc3,0xbac2baf6,
0xaa483a6d,0xb67cbbfa,0xbbfeb8c4,0x3b502cb5,0xbb3bbadd,0x3be238ec,0x36d7b81d,0xb1793a4f,0x39edb0b2,0xb9843505,0x395f3bea,0xb9cbbb99,
0xae46bba8,0x39843b25,0x3bf634a5,0xb9cb3732,0x3a2f3b0e,0xbbceb7e3,0xb913378b,0x3303baf6,0xbbf6b4a5,0x3b77acb5,0xae46bba8,0x35c23bfa,
0x3913b78b,0xb89b38ec,0x3a2f3b0e,0xba8aba4f,0xbbeab564,0x3af6b67c,0x30b2bb88,0x37e33b50,0x3bc3aa48,0xba0f389b,0x33c63bfe,0xb93aba8a,
0xba6d36d7,0x38ecb9cb,0xb8c4bb3b,0x3a4f3984,0x381db9ed,0xb7323ac2,0x3add395f,0xbb25b848,0xb61f3b64,0xb444bb77,0xbb64b61f,0x3bb6b5c2,
0x361fbb64,0x2cb53be2,0x3b64361f,0xbbfa3179,0xb61f3b64,0x2fd6bbff,0xbb64b61f,0x3bf12648,0x361fbb64,0xb5053bce,0x3b64361f,0xbb99b303,
0x3a6d36d7,0xbbff3505,0xb8c43b3b,0xa648bb99,0xb81db9ed,0x3ac23444,0x3addb95f,0xb8483bb6,0x30b23b88,0xb67cba0f,0xbbea3564,0x3b50b93a,
0x33c6bbfe,0xb1793bf1,0x3bc32a48,0xbbe22fd6,0x3a2fbb0e,0xb3033bb6,0x3913378b,0xbbce3444,0xbbf634a5,0x3b77ba0f,0x2e46bba8,0x35c2393a,
0x3913378b,0xba8aafd6,0xba2f3b0e,0x389bbbf1,0x2e46bba8,0xa6483b25,0x3bf6b4a5,0xbbff3732,0xb6d7b81d,0x3b25b303,0x3b3bbadd,0xb7323bce,
0xb95f3bea,0x3444bb50,0xb9edb0b2,0x3bb6b67c,0x3b88b3c6,0xbbfa389b,0xb5643bc3,0x2cb5ba8a,0xaa48ba6d,0x2fd63984,0x3bfeb8c4,0xbbf139cb,
0xbbd93aa7,0x393abbe2,0xb23eb872,0x3a0fb179,0x323e3872,0xb8eca648,0xbbd93aa7,0x3a4fbbff,0x3bd9baa7,0xbb253bce,0x323e3872,0xb732b303,
0xb23eb872,0x3444367c,0x3bd9baa7,0xbbb63b50,0xaa4838c4,0xb89b2fd6,0xbbfe3a6d,0x3a8abbf1,0x3b3bb81d,0xbbff3b25,0xb6d73add,0xa648b732,
0x39edbbea,0xb8483af6,0x395fb0b2,0xbac237e3,0xb564b3c6,0x367c2cb5,0x3b88bbc3,0xbb503bfa,0x3ba8ba2f,0xbb773bfa,0xb4a53913,0xb5c22cb5,
0x3b0ebbf6,0xb89b3a4f,0x378bae46,0xba8a38ec,0x34a5b913,0xa6483505,0x3ba8ba2f,0xbbff3b99,0xb78b2e46,0x3848b444,0x3b0ebbf6,0xbac23bb6,
0x381db95f,0x2fd6a648,0x3addb9ed,0xbbf13bff,0x30b2b564,0x3505b303,0x3beabb88,0xbb993bce,0xb3c62a48,0x37e3b67c,0x3bc3bbfe,0xbaf63b50,
0xb8c436d7,0x393ab89b,0x3a6dbb3b,0xba0f3a8a,0xb9a839a8,0x3bf1bbff,0x39a8b9a8,0xafd62648,0xb9a839a8,0x3b99bbce,0x39a8b9a8,0xb5053303,
0xb9a839a8,0x3af6bb50,0x39a8b9a8,0xb7e3367c,0xb9a839a8,0x3a0fba8a,0x39a8b9a8,0xb93a389b,0xbadd39ed,0x35c2acb5,0xb81d395f,0x3b77bbfa,
0xbbea3b88,0x3a8ab8ec,0xb0b23564,0x389bba4f,0xbbc33bfe,0x3bffbb99,0x33c6aa48,0x2648b505,0xba6d3b3b,0x3ac2bbb6,0x38c4b6d7,0xb8483444,
0x34a5b913,0xba8a3bf1,0xbba83a2f,0x389bafd6,0xb78b2e46,0x26483732,0xbb0e3bf6,0x3bffbb25,0xbba83a2f,0x3ac2b7e3,0xb4a53913,0x3848baf6,
0xbb0e3bf6,0x3b50bbfa,0x378bae46,0xb67cacb5,0x3bfeba6d,0xba0f3179,0x2a48b8c4,0xb93a3be2,0x36d7badd,0xba4f3bff,0xbb3b381d,0x38ec2648,
0xb95f30b2,0x37323303,0xb9ed3bea,0x3b25bbce,0xbb883bc3,0x3bb6bb50,0x356433c6,0xb444b67c,0x323e3872,0x3732bbce,0x3bd9baa7,0xbb253303,
0x3bd9baa7,0xbbb6367c,0xb23eb872,0xb4443b50,0xb23eb872,0xacb53a8a,0xbbd93aa7,0x3bfab89b,0xbbd93aa7,0x3bf1b9cb,0x323e3872,0xafd6b984,
0xbb3b3add,0x3bceb444,0x36d7381d,0x3303bbb6,0x39ed30b2,0xb5c2b93a,0x395fbbea,0xbb773a0f,0x3564bbc3,0xb89b3bf1,0xbb8833c6,0x3a8a2fd6,
0xbbfe38c4,0x3bffb732,0x2a483a6d,0x2648bb25,0xb913b78b,0x26483b99,0xba2f3b0e,0x3bffb505,0xae463ba8,0x3848bbb6,0x3bf6b4a5,0xbac2b444,
0x3a2fbb0e,0xbb50393a,0xb913b78b,0x367c3a0f,0xbbf634a5,0x3be2afd6,0xae463ba8,0x3179bbf1,0x38c4bb3b,0xbbb635c2,0xba6db6d7,0x34443b77,
0xbadd395f,0x3bfab179,0x381d39ed,0xacb5bbe2,0x3beab564,0xbbf1a648,0xb0b2bb88,0xafd63bff,0xbbc3aa48,0x3b993303,0xb3c63bfe,0x3505bbce,
0x3b64361f,0xb7e3bb50,0x361fbb64,0xbaf6367c,0xbb64b61f,0x393a3a8a,0xb61f3b64,0x3a0fb89b,0x3b64361f,0xba4fb984,0x361fbb64,0xb8ec39cb,
0xbb64b61f,0x3b253848,0xb61f3b64,0x3732bac2,0xb0b23b88,0x39cbb732,0x3bea3564,0xb984bb25,0xb3c6bbfe,0xb3033af6,0xbbc32a48,0x3bce37e3,
0x38c43b3b,0xb5c2bbfa,0x3a6db6d7,0xbb772cb5,0xbaddb95f,0x3a8a3a4f,0xb81d39ed,0x389bb8ec,0xbbf6b4a5,0x3ac23af6,0x2e463ba8,0x3848b7e3,
0x3913b78b,0xbb50acb5,0xba2fbb0e,0x367c3bfa,0x2e463ba8,0x3179ba4f,0x3bf634a5,0xbbe2b8ec,0xba2fbb0e,0x39cb3b99,0xb913378b,0x3984b505,
0xb564bbc3,0xb5053848,0xbb88b3c6,0x3b993ac2,0x3bfe38c4,0xbaf6bb77,0x2a48ba6d,0xb7e335c2,0xb6d7381d,0x393ab179,0x3b3b3add,0xba0fbbe2,
0xb95fbbea,0x38ec3bff,0xb9ed30b2,0x3a4f2648,0x3aa7323e,0xbbfaba8a,0xb872bbd9,0xacb5389b,0x38723bd9,0xafd6b9cb,0x3aa7323e,0xbbf1b984,
0xbaa7b23e,0x3b993848,0x38723bd9,0xb505bac2,0xb872bbd9,0x37e33b77,0xbaa7b23e,0x3af635c2,0x39ed3bea,0xb179b8ec,0x395f30b2,0xbbe2ba4f,
0xb56433c6,0x39cb3505,0x3b883bc3,0xb984bb99,0xbbfeba6d,0x3bce3bb6,0x2a4838c4,0x3303b444,0xb6d7badd,0x35c23a0f,0xbb3bb81d,0x3b77393a,
0xb78bae46,0x3b503a0f,0x3b0e3bf6,0xb67cb93a,0xbba8ba2f,0x3be23bf1,0x34a53913,0x3179afd6,0xbb0ebbf6,0x39cb3b25,0xb78bae46,0x39843732,
0xb4a5b913,0x330337e3,0xbba8ba2f,0x3bce3af6,0xbbc3bbfe,0x38ec3984,0xb3c6aa48,0x3a4f39cb,0xba6dbb3b,0x37323848,0xb8c4b6d7,0x3b253ac2,
0xb81db95f,0x344435c2,0xbaddb9ed,0x3bb63b77,0xb0b2b564,0x2cb53179,0xbbeabb88,0x3bfa3be2,0x3c003c00,0x3a4f39cb,0,0x38ec3984,
0x3c003c00,0x3b253ac2,0,0x37323848,0x3c003c00,0x3bb63b77,0,0x344435c2,0x3c003c00,0x3bfa3be2,0,0x2cb53179,
0x33c62a48,0xb67cb93a,0x3bc33bfe,0x3b503a0f,0x38c436d7,0x3179afd6,0x3a6d3b3b,0x3be23bf1,0x3add39ed,0x39843732,0x381d395f,0x39cb3b25,
0x3bea3b88,0x3bce3af6,0x30b23564,0x330337e3,0xbb0ebbf6,0xbbe2ba4f,0x378b2e46,0xb179b8ec,0xb4a5b913,0xb984bb99,0x3ba83a2f,0x39cb3505,
0x378b2e46,0x3303b444,0x3b0e3bf6,0x3bce3bb6,0x3ba83a2f,0x3b77393a,0x34a53913,0x35c23a0f,0xb95fb0b2,0xacb5389b,0xb9edbbea,0xbbfaba8a,
0xbb88bbc3,0xbbf1b984,0x3564b3c6,0xafd6b9cb,0xaa48b8c4,0xb505bac2,0x3bfe3a6d,0x3b993848,0x3b3b381d,0x3af635c2,0x36d73add,0x37e33b77,
0x38723bd9,0x3b993ac2,0xbaa7b23e,0xb5053848,0xbaa7b23e,0xb7e335c2,0xb872bbd9,0xbaf6bb77,0xb872bbd9,0xba0fbbe2,0x3aa7323e,0x393ab179,
0x3aa7323e,0x3a4f2648,0x38723bd9,0x38ec3bff,0x3b8833c6,0x3848b7e3,0x35643bc3,0x3ac23af6,0xaa483a6d,0x367c3bfa,0xbbfeb8c4,0xbb50acb5,
0xbb3bbadd,0xbbe2b8ec,0x36d7b81d,0x3179ba4f,0x39edb0b2,0x3984b505,0x395f3bea,0x39cb3b99,0xae46bba8,0xb984bb25,0x3bf634a5,0x39cbb732,
0x3a2f3b0e,0x3bce37e3,0xb913378b,0xb3033af6,0xbbf6b4a5,0xbb772cb5,0xae46bba8,0xb5c2bbfa,0x3913b78b,0x389bb8ec,0x3a2f3b0e,0x3a8a3a4f,
0xbbeab564,0xbaf6367c,0x30b2bb88,0xb7e3bb50,0x3bc3aa48,0x3a0fb89b,0x33c63bfe,0x393a3a8a,0xba6d36d7,0xb8ec39cb,0xb8c4bb3b,0xba4fb984,
0x381db9ed,0x3732bac2,0x3add395f,0x3b253848,0xb61f3b64,0x34443b77,0xbb64b61f,0xbbb635c2,0x361fbb64,0xacb5bbe2,0x3b64361f,0x3bfab179,
0xb61f3b64,0xafd63bff,0xbb64b61f,0xbbf1a648,0x361fbb64,0x3505bbce,0x3b64361f,0x3b993303,0x3a6d36d7,0x3bffb505,0xb8c43b3b,0x26483b99,
0xb81db9ed,0xbac2b444,0x3addb95f,0x3848bbb6,0x30b23b88,0x367c3a0f,0xbbea3564,0xbb50393a,0x33c6bbfe,0x3179bbf1,0x3bc32a48,0x3be2afd6,
0x3a2fbb0e,0x3303bbb6,0x3913378b,0x3bceb444,0xbbf634a5,0xbb773a0f,0x2e46bba8,0xb5c2b93a,0x3913378b,0x3a8a2fd6,0xba2f3b0e,0xb89b3bf1,
0x2e46bba8,0x2648bb25,0x3bf6b4a5,0x3bffb732,0xb6d7b81d,0xbb253303,0x3b3bbadd,0x3732bbce,0xb95f3bea,0xb4443b50,0xb9edb0b2,0xbbb6367c,
0x3b88b3c6,0x3bfab89b,0xb5643bc3,0xacb53a8a,0xaa48ba6d,0xafd6b984,0x3bfeb8c4,0x3bf1b9cb,0xbbd93aa7,0xb93a3be2,0xb23eb872,0xba0f3179,
0x323e3872,0x38ec2648,0xbbd93aa7,0xba4f3bff,0x3bd9baa7,0x3b25bbce,0x323e3872,0x37323303,0xb23eb872,0xb444b67c,0x3bd9baa7,0x3bb6bb50,
0xaa4838c4,0x389bafd6,0xbbfe3a6d,0xba8a3bf1,0x3b3bb81d,0x3bffbb25,0xb6d73add,0x26483732,0x39edbbea,0x3848baf6,0x395fb0b2,0x3ac2b7e3,
0xb564b3c6,0xb67cacb5,0x3b88bbc3,0x3b50bbfa,0x3ba8ba2f,0x3b77bbfa,0xb4a53913,0x35c2acb5,0x3b0ebbf6,0x389bba4f,0x378bae46,0x3a8ab8ec,
0x34a5b913,0x2648b505,0x3ba8ba2f,0x3bffbb99,0xb78b2e46,0xb8483444,0x3b0ebbf6,0x3ac2bbb6,0x381db95f,0xafd62648,0x3addb9ed,0x3bf1bbff,
0x30b2b564,0xb5053303,0x3beabb88,0x3b99bbce,0xb3c62a48,0xb7e3367c,0x3bc3bbfe,0x3af6bb50,0xb8c436d7,0xb93a389b,0x3a6dbb3b,0x3a0fba8a,
0xb9a839a8,0xbbf13bff,0x39a8b9a8,0x2fd6a648,0xb9a839a8,0xbb993bce,0x39a8b9a8,0x3505b303,0xb9a839a8,0xbaf63b50,0x39a8b9a8,0x37e3b67c,
0xb9a839a8,0xba0f3a8a,0x39a8b9a8,0x393ab89b,0xbadd39ed,0xb5c22cb5,0xb81d395f,0xbb773bfa,0xbbea3b88,0xba8a38ec,0xb0b23564,0xb89b3a4f,
0xbbc33bfe,0xbbff3b99,0x33c6aa48,0xa6483505,0xba6d3b3b,0xbac23bb6,0x38c4b6d7,0x3848b444,0x34a5b913,0x3a8abbf1,0xbba83a2f,0xb89b2fd6,
0xb78b2e46,0xa648b732,0xbb0e3bf6,0xbbff3b25,0xbba83a2f,0xbac237e3,0xb4a53913,0xb8483af6,0xbb0e3bf6,0xbb503bfa,0x378bae46,0x367c2cb5,
0x3bfeba6d,0x3a0fb179,0x2a48b8c4,0x393abbe2,0x36d7badd,0x3a4fbbff,0xbb3b381d,0xb8eca648,0xb95f30b2,0xb732b303,0xb9ed3bea,0xbb253bce,
0xbb883bc3,0xbbb63b50,0x356433c6,0x3444367c,0x323e3872,0xb7323bce,0x3bd9baa7,0x3b25b303,0x3bd9baa7,0x3bb6b67c,0xb23eb872,0x3444bb50,
0xb23eb872,0x2cb5ba8a,0xbbd93aa7,0xbbfa389b,0xbbd93aa7,0xbbf139cb,0x323e3872,0x2fd63984,0xbb3b3add,0xbbce3444,0x36d7381d,0xb3033bb6,
0x39ed30b2,0x35c2393a,0x395fbbea,0x3b77ba0f,0x3564bbc3,0x389bbbf1,0xbb8833c6,0xba8aafd6,0xbbfe38c4,0xbbff3732,0x2a483a6d,0xa6483b25,
0xb913b78b,0xa648bb99,0xba2f3b0e,0xbbff3505,0xae463ba8,0xb8483bb6,0x3bf6b4a5,0x3ac23444,0x3a2fbb0e,0x3b50b93a,0xb913b78b,0xb67cba0f,
0xbbf634a5,0xbbe22fd6,0xae463ba8,0xb1793bf1,0x38c4bb3b,0x3bb6b5c2,0xba6db6d7,0xb444bb77,0xbadd395f,0xbbfa3179,0x381d39ed,0x2cb53be2,
0x3beab564,0x3bf12648,0xb0b2bb88,0x2fd6bbff,0xbbc3aa48,0xbb99b303,0xb3c63bfe,0xb5053bce,0x3b64361f,0x37e33b50,0x361fbb64,0x3af6b67c,
0xbb64b61f,0xb93aba8a,0xb61f3b64,0xba0f389b,0x3b64361f,0x3a4f3984,0x361fbb64,0x38ecb9cb,0xbb64b61f,0xbb25b848,0xb61f3b64,0xb7323ac2,
0xb0b23b88,0xb9cb3732,0x3bea3564,0x39843b25,0xb3c6bbfe,0x3303baf6,0xbbc32a48,0xbbceb7e3,0x38c43b3b,0x35c23bfa,0x3a6db6d7,0x3b77acb5,
0xbaddb95f,0xba8aba4f,0xb81d39ed,0xb89b38ec,0xbbf6b4a5,0xbac2baf6,0x2e463ba8,0xb84837e3,0x3913b78b,0x3b502cb5,0xba2fbb0e,0xb67cbbfa,
0x2e463ba8,0xb1793a4f,0x3bf634a5,0x3be238ec,0xba2fbb0e,0xb9cbbb99,0xb913378b,0xb9843505,0xb564bbc3,0x3505b848,0xbb88b3c6,0xbb99bac2,
0x3bfe38c4,0x3af63b77,0x2a48ba6d,0x37e3b5c2,0xb6d7381d,0xb93a3179,0x3b3b3add,0x3a0f3be2,0xb95fbbea,0xb8ecbbff,0xb9ed30b2,0xba4fa648,
0x3aa7323e,0x3bfa3a8a,0xb872bbd9,0x2cb5b89b,0x38723bd9,0x2fd639cb,0x3aa7323e,0x3bf13984,0xbaa7b23e,0xbb99b848,0x38723bd9,0x35053ac2,
0xb872bbd9,0xb7e3bb77,0xbaa7b23e,0xbaf6b5c2,0x39ed3bea,0x317938ec,0x395f30b2,0x3be23a4f,0xb56433c6,0xb9cbb505,0x3b883bc3,0x39843b99,
0xbbfeba6d,0xbbcebbb6,0x2a4838c4,0xb3033444,0xb6d7badd,0xb5c2ba0f,0xbb3bb81d,0xbb77b93a,0xb78bae46,0xbb50ba0f,0x3b0e3bf6,0x367c393a,
0xbba8ba2f,0xbbe2bbf1,0x34a53913,0xb1792fd6,0xbb0ebbf6,0xb9cbbb25,0xb78bae46,0xb984b732,0xb4a5b913,0xb303b7e3,0xbba8ba2f,0xbbcebaf6,
0xbbc3bbfe,0xb8ecb984,0xb3c6aa48,0xba4fb9cb,0xba6dbb3b,0xb732b848,0xb8c4b6d7,0xbb25bac2,0xb81db95f,0xb444b5c2,0xbaddb9ed,0xbbb6bb77,
0xb0b2b564,0xacb5b179,0xbbeabb88,0xbbfabbe2,0x3c003c00,0x96480000,0x3c003c00,0xa311a248,0x3c003c00,0x9cb69a48,0x3c003c00,0xa452a3db,
0x3c003c00,0x9fdb9e48,0x3c003c00,0xa51ba4b6,0x3c003c00,0xa17fa0b6,0x3bff3c00,0xa5e4a57f,0x3c003c00,0x9fdb0000,0x3bfb3bfc,0xac6aabd9,
0x3bff3c00,0xa5e4a3db,0x3bf93bfa,0xad65ace7,0x3bfe3bff,0xa8e8a7da,0x3bf63bf7,0xae5fade2,0x3bfd3bfe,0xaadea9e3,0x3bf23bf4,0xaf59aedc,
0x3c003c00,0xa3110000,0x3bf03bf4,0xafefaf0e,0x3bfe3bff,0xa94da711,0x3be83bed,0xb0d7b067,0x3bfb3bfd,0xac6aab11,0x3bdf3be4,0xb1b6b147,
0x3bf63bf9,0xae2dad4c,0x3bd43bda,0xb294b226,0x3c003c00,0xa51b0000,0x3bdf3be6,0xb1b6b115,0x3bfc3bfe,0xaba7a91b,0x3bcf3bd7,0xb2f7b257,
0x3bf63bf9,0xae5fad1a,0x3bbc3bc6,0xb41ab396,0x3bec3bf1,0xb074afa4,0x3ba53bb1,0xb4b7b469,0x3bff3c00,0xa6ad0000,0x3bc83bd4,0xb371b2a1,
0x3bfa3bfd,0xad00aaac,0x3bac3bbb,0xb487b420,0x3bef3bf5,0xb029aeaa,0x3b8b3b9d,0xb552b4ed,0x3bde3be7,0xb1cfb0fd,0x3b653b79,0xb61ab5b6,
0x3bff3c00,0xa81f0000,0x3bab3bbc,0xb493b414,0x3bf63bfc,0xae2dac1f,0x3b813b97,0xb58db511,0x3be53bef,0xb122b01d,0x3b4f3b69,0xb682b608,
0x3bcc3bda,0xb328b226,0x3b163b33,0xb76fb6f9,0x3bfe3c00,0xa8e80000,0x3b873ba0,0xb56ab4d5,0x3bf23bfa,0xaf59ace7,0x3b4c3b6b,0xb68db5fd,
0x3bda3be8,0xb219b0e4,0x3b073b2b,0xb7a6b71b,0x3bb73bca,0xb43eb34c,0x3ab63ae0,0xb85ab817,0x3bfe3c00,0xa9b10000,0x3b5e3b80,0xb63cb593,
0x3bee3bf8,0xb042adb0,0x3b103b39,0xb785b6e3,0x3bce3be0,0xb30fb1aa,0x3ab33ae3,0xb85fb812,0x3b9e3bb7,0xb4e7b438,0x3a493a7f,0xb8f3b8ab,
0x3bfd3c00,0xaa7a0000,0x3b2f3b5a,0xb70ab64e,0x3be83bf6,0xb0d7ae78,0x3acb3aff,0xb83ab7c2,0x3bbf3bd6,0xb402b26f,0x3a543a92,0xb8e5b891,
0x3b813ba2,0xb58db4c9,0x39cd3a13,0xb982b935,0x3bfd3c00,0xab430000,0x3afb3b30,0xb7d2b705,0x3be23bf3,0xb16caf40,0x3a7e3abf,0xb8adb84d,
0x3bae3bcb,0xb47bb334,0x39eb3a37,0xb962b909,0x3b603b8a,0xb631b558,0x3946399b,0xba04b9b5,0x3bfc3c00,0xac060000,0x3ac13b02,0xb84ab7b7,
0x3bdc3bf0,0xb201b004,0x3a293a78,0xb91bb8b5,0x3b9c3bc0,0xb4f3b3f7,0x397939d4,0xb9d6b97b,0x3b3d3b70,0xb6d2b5e5,0x38b23918,0xba7aba2b,
0x3bfb3c00,0xac6a0000,0x3a813ad0,0xb8a8b832,0x3bd43bed,0xb294b067,0x39cd3a2b,0xb982b918,0x3b873bb2,0xb56ab45d,0x38fd3969,0xba41b9e5,
0x3b163b53,0xb76fb670,0x3815388c,0xbae1ba95,0x3bfa3c00,0xacce0000,0x3a3d3a99,0xb902b887,0x3bcc3be9,0xb328b0cb,0x396b39d8,0xb9e3b976,
0x3b713ba4,0xb5dfb4bd,0x387a38f6,0xbaa2ba47,0x3aeb3b33,0xb805b6f9,0x36dd37ee,0xbb3abaf3,0x3bf93c00,0xad330000,0x39f43a5e,0xb958b8d8,
0x3bc33be5,0xb3bab12e,0x39023980,0xba3db9d0,0x3b593b95,0xb654b51d,0x37dd387c,0xbaf7baa0,0x3abd3b11,0xb850b780,0x358136b5,0xbb83bb43,
0x3bf83c00,0xad970000,0x39a63a1f,0xb9aab927,0x3bba3be1,0xb426b191,0x38943922,0xba90ba23,0x3b3f3b84,0xb6c6b57c,0x36bb37f9,0xbb42baf0,
0x3a8c3aed,0xb899b802,0x341a3570,0xbbbcbb86,0x3bf73c00,0xadfb0000,0x395439dc,0xb9f8b972,0x3bb03bdc,0xb46fb1f4,0x382038bf,0xbadbba71,
0x3b243b72,0xb737b5da,0x358d36ee,0xbb81bb36,0x3a583ac6,0xb8e0b842,0x31533420,0xbbe3bbbb,0x3bf63c00,0xae5f0000,0x38fd3996,0xba41b9ba,
0x3ba53bd7,0xb4b7b257,0x374e3858,0xbb1ebab8,0x3b073b5f,0xb7a6b637,0x345735da,0xbbb3bb72,0x3a213a9c,0xb924b881,0x2cce3191,0xbbfabbe1,
0x3bf53c00,0xaec30000,0x38a3394d,0xba85b9fe,0x3b9a3bd2,0xb4ffb2b9,0x365437d8,0xbb59baf9,0x3ae83b4b,0xb80ab693,0x323234bd,0xbbd9bba4,
0x39e73a71,0xb966b8bf,0xa4522db0,0xbc00bbf8,0x3bf33c00,0xaf270000,0x38453900,0xbac4ba3f,0x3b8e3bcd,0xb546b31b,0x355236f9,0xbb8bbb33,
0x3ac73b36,0xb840b6ee,0x2f593334,0xbbf2bbcb,0x39aa3a43,0xb9a6b8fb,0xaef51a48,0xbbf4bc00,0x3bf23c00,0xaf8b0000,0x37c838b0,0xbafeba7c,
0x3b813bc7,0xb58db37d,0x344b3614,0xbbb5bb67,0x3aa53b20,0xb874b748,0x288430e4,0xbbffbbe8,0x396b3a13,0xb9e3b935,0xb263ad4c,0xbbd7bbf9,
0x3bf03c00,0xafef0000,0x36ff385d,0xbb32bab5,0x3b733bc1,0xb5d4b3df,0x327c3529,0xbbd6bb93,0x3a813b08,0xb8a8b7a1,0xa9b12d1a,0xbbfebbf9,
0x392939e1,0xba1db96d,0xb49fb160,0xbba9bbe3,0x3bef3c00,0xb0290000,0x36313807,0xbb60bae9,0x3b653bbb,0xb61ab420,0x305b3438,0xbbedbbb7,
0x3a5c3af0,0xb8dbb7f9,0xafef1e48,0xbbf0bc00,0x38e539ad,0xba54b9a4,0xb602b408,0xbb6abbbe,0x3bed3c00,0xb05b0000,0x355e375e,0xbb89bb1a,
0x3b573bb4,0xb65fb451,0x2c6a3288,0xbbfbbbd5,0x3a353ad6,0xb90cb828,0xb27cac51,0xbbd6bbfb,0x389e3976,0xba89b9d8,0xb759b558,0xbb1bbb8a,
0x3beb3c00,0xb08d0000,0x348736aa,0xbbacbb46,0x3b473bad,0xb6a4b481,0x16483099,0xbc00bbeb,0x3a0d3abc,0xb93cb852,0xb47bb080,0xbbaebbec,
0x3855393e,0xbababa0b,0xb850b69e,0xbabdbb49,0x3be93c00,0xb0be0000,0x335935f1,0xbbc9bb6e,0x3b373ba6,0xb6e8b4b1,0xac382d4c,0xbbfcbbf9,
0x39e33aa0,0xb96bb87c,0xb5b1b2d2,0xbb7abbd1,0x380a3905,0xbae8ba3b,0xb8eab7d8,0xba50baf9,0x3be73c00,0xb0f00000,0x319e3534,0xbbe0bb91,
0x3b273b9e,0xb72cb4e1,0xb042257f,0xbbeebc00,0x39b83a83,0xb999b8a6,0xb6ddb48d,0xbb3abbab,0x377a38c9,0xbb13ba69,0xb979b881,0xb9d6ba9c,
0x3be53c00,0xb1220000,0x2fbd3475,0xbbf1bbaf,0x3b163b97,0xb76fb511,0xb263a91b,0xbbd7bbfe,0x398b3a65,0xb9c5b8ce,0xb7feb5ab,0xbaeebb7b,
0x36dd388c,0xbb3aba95,0xb9fcb90e,0xb94fba33,0x3be33c00,0xb1530000,0x2c383365,0xbbfcbbc9,0x3b043b8f,0xb7b2b540,0xb43eae78,0xbbb7bbf6,
0x395d3a47,0xb9f0b8f6,0xb889b6c1,0xba97bb41,0x363c384d,0xbb5ebabf,0xba73b992,0xb8bcb9be,0x3be13c00,0xb1850000,0x217f31db,0xbc00bbdd,
0x3af13b86,0xb7f3b570,0xb546b12e,0xbb8ebbe5,0x392e3a27,0xba19b91d,0xb90cb7cd,0xba35bafc,0x3599380d,0xbb7fbae6,0xbadbba0b,0xb820b93e,
0x3bdf3c00,0xb1b60000,0xa9b1304e,0xbbfebbed,0x3ade3b7d,0xb81ab59f,0xb648b31b,0xbb5cbbcd,0x38fd3a07,0xba41b943,0xb986b867,0xb9c9baae,
0x34f33796,0xbb9cbb0b,0xbb35ba78,0xb6f4b8b5,0x3bdd3c00,0xb1e80000,0xae5f2d7e,0xbbf6bbf8,0x3acb3b74,0xb83ab5ce,0xb742b481,0xbb21bbad,
0x38cc39e5,0xba67b969,0xb9f8b8e2,0xb954ba56,0x344b3710,0xbbb5bb2e,0xbb7fbad9,0xb599b822,0x3bda3c00,0xb2190000,0xb0f028b6,0xbbe7bbff,
0x3ab63b6b,0xb85ab5fd,0xb81ab570,0xbadebb86,0x389939c3,0xba8cb98d,0xba60b956,0xb8d6b9f6,0x33403687,0xbbcbbb4e,0xbbb8bb2e,0xb432b710,
0x3bff3bff,0xa6ada648,0x3bfe3bff,0xa8e8a8b6,0x3bff3bff,0xa776a711,0x3bfe3bfe,0xa94da91b,0x3bff3bff,0xa81fa7da,0x3bfe3bfe,0xa9b1a97f,
0x3bff3bff,0xa884a852,0x3bfe3bfe,0xaa16a9e3,0x3bef3bf1,0xb029afd6,0x3bda3bdd,0xb219b1db,0x3bea3bed,0xb0a6b067,0x3bd43bd7,0xb294b257,
0x3be53be8,0xb122b0e4,0x3bce3bd1,0xb30fb2d2,0x3be03be3,0xb19eb160,0x3bc63bca,0xb389b34c,0x3bc83bce,0xb371b303,0x3b873b91,0xb56ab534,
0x3bba3bc1,0xb426b3df,0x3b733b7d,0xb5d4b59f,0x3bab3bb2,0xb493b45d,0x3b5e3b69,0xb63cb608,0x3b9a3ba2,0xb4ffb4c9,0x3b473b53,0xb6a4b670,
0x3b8b3b99,0xb552b505,0x3b073b1a,0xb7a6b75e,0x3b6f3b7d,0xb5ebb59f,0x3ade3af3,0xb81ab7ee,0x3b4f3b5f,0xb682b637,0x3ab33ac9,0xb85fb83d,
0x3b2c3b3e,0xb715b6cc,0x3a853a9c,0xb8a3b881,0x3b3a3b50,0xb6ddb67c,0x3a5c3a7c,0xb8dbb8b0,0x3b0a3b22,0xb79bb73d,0x3a193a3b,0xb92eb905,
0x3ad53af0,0xb82ab7f9,0x39d239f6,0xb97db956,0x3a9b3ab8,0xb884b858,0x398639ad,0xb9c9b9a4,0x3ad53af6,0xb82ab7e3,0x398b39ba,0xb9c5b996,
0x3a8c3ab1,0xb899b862,0x3929395b,0xba1db9f2,0x3a3d3a65,0xb902b8ce,0x38c138f6,0xba6fba47,0x39e73a13,0xb966b935,0x3855388c,0xbababa95,
0x3a5c3a8a,0xb8dbb89b,0x389938d8,0xba8cba5e,0x39f83a2b,0xb954b918,0x38153858,0xbae1bab8,0x398b39c3,0xb9c5b98d,0x371537a1,0xbb2cbb08,
0x39163951,0xba2db9fa,0x35f73687,0xbb6cbb4e,0x39d23a0f,0xb97db93a,0x371537b7,0xbb2cbb02,0x394f3992,0xb9fcb9be,0x35c83670,0xbb76bb53,
0x38c13909,0xba6fba37,0x346f351d,0xbbb0bb95,0x382a3877,0xbad5baa3,0x3219337d,0xbbdabbc7,0x39373984,0xba11b9cb,0x34cf3593,0xbba1bb80,
0x389438e7,0xba90ba52,0x327c3408,0xbbd6bbbe,0x37c8383d,0xbafebac9,0x2e9130e4,0xbbf5bbe8,0x36543710,0xbb59bb2e,0x16482aac,0xbc00bbfd,
0x388e38ec,0xba93ba4f,0x30d732a1,0xbbe8bbd4,0x3790382d,0xbb0dbad3,0x28e82e14,0xbbfebbf7,0x35eb36c1,0xbb6fbb41,0xaccea4b6,0xbbfabc00,
0x34323511,0xbbb8bb97,0xb201b036,0xbbdcbbee,0x37b23848,0xbb04bac2,0x96482bd9,0xbc00bbfc,0x35df36cc,0xbb71bb3e,0xb010ac1f,0xbbefbbfc,
0x33eb34ed,0xbbc0bb9d,0xb402b20d,0xbbbfbbdb,0x2fef31f4,0xbbf0bbdc,0xb5ebb4f9,0xbb6fbb9b,0x36313732,0xbb60bb25,0xb0f0ad7e,0xbbe7bbf8,
0x341a3529,0xbbbcbb93,0xb49fb31b,0xbba9bbcd,0x2fbd320d,0xbbf1bbdb,0xb6afb5ab,0xbb45bb7b,0xa4522aac,0xbc00bbfd,0xb850b7ac,0xbabdbb05,
0x349f35c2,0xbba9bb77,0xb4dbb365,0xbb9fbbc9,0x308d32ea,0xbbebbbd0,0xb715b5fd,0xbb2cbb6b,0x9fdb2c51,0xbc00bbfb,0xb894b812,0xba90bae3,
0xb109ad4c,0xbbe6bbf9,0xb982b90e,0xb9cdba33,0x32013444,0xbbdcbbb6,0xb721b5f1,0xbb2abb6e,0x26ad2edc,0xbbffbbf4,0xb8adb822,0xba7ebad9,
0xb05bab11,0xbbedbbfd,0xb9aab930,0xb9a6ba17,0xb4b7b2ea,0xbba5bbd0,0xba81ba1b,0xb8a8b92b,0x2d653179,0xbbf9bbe2,0xb89eb807,0xba89bae9,
0xadc99a48,0xbbf8bc00,0xb9afb92b,0xb9a1ba1b,0xb432b1aa,0xbbb8bbe0,0xba93ba27,0xb88eb91d,0xb6d2b587,0xbb3dbb82,0xbb45baf3,0xb6afb7ee,
0xa51b2cb5,0xbc00bbfa,0xb990b900,0xb9c0ba3f,0xb294af40,0xbbd4bbf3,0xba89ba13,0xb89eb935,0xb625b4bd,0xbb63bba4,0xbb47baf0,0xb6a4b7f9,
0xb865b780,0xbab0bb11,0xbbc5bb8f,0xb3a2b540,0xafefa648,0xbbf0bbff,0xba60b9dc,0xb8d6b972,0xb517b31b,0xbb96bbcd,0xbb35bad3,0xb6f4b82d,
0xb7feb693,0xbaeebb4b,0xbbc0bb84,0xb3ebb57c,0xb94ab8ab,0xba00ba7f,0xbbfdbbe9,0xaa7ab0cb,0xb340afd6,0xbbcbbbf1,0xbb0aba99,0xb79bb887,
0xb6d2b540,0xbb3dbb8f,0xbbaebb67,0xb47bb614,0xb8dbb828,0xba5cbad6,0xbbfbbbe0,0xac9cb1aa,0xba15b980,0xb933b9d0,0xbbecbbff,0x30742852,
0xb53ab303,0xbb90bbce,0xbb89bb30,0xb55eb705,0xb83ab6e3,0xbacbbb39,0xbbf2bbca,0xaf8bb34c,0xb9a1b8f6,0xb9afba47,0xbbf5bc00,0x2ec39e48,
0xbac1ba3b,0xb84ab905,0xbb92bbd0,0x352f32ea,0xb6c6b505,0xbb3fbb99,0xbbdcbba0,0xb201b4d5,0xb8fdb838,0xba41bacc,0xbbfebbfb,0x2a16ac83,
0xba50b9b1,0xb8eab99f,0xbbaebbe4,0x347b3147,0xbb4abad9,0xb699b822,0xbaf1bb5d,0x37f33642,0xb820b67c,0xbadbbb50,0xbbffbbe6,0xa884b115,
0xb9afb8f1,0xb9a1ba4b,0xbbd2bbf8,0x32c62db0,0xbae5ba56,0xb80fb8e2,0xbb2abb8c,0x3721354c,0xbbaebb58,0xb47bb659,0xba11baaa,0x3937386d,
0xb8d1b7e3,0xba64baf6,0xbbf2bc00,0x2f8ba248,0xba4db99b,0xb8eeb9b5,0xbb6fbbc1,0x35eb33df,0xbb5cbae3,0xb648b812,0xba6bbafc,0x38c737cd,
0xbbebbbb4,0xb08db451,0xb8f8b9be,0x3a453992,0xb974b89b,0xb9daba8a,0xbbb5bbed,0x344b304e,0xbad5ba33,0xb82ab90e,0xbad8bb58,0x38253659,
0xbbb3bb55,0xb457b665,0xb979ba37,0x39d63909,0xbc00bbed,0x9648b067,0xb764b8a0,0x3b183a87,0xba09b93a,0xb941ba0f,0xbb4abbaf,0x36993475,
0xbb45bab8,0xb6afb858,0xba11babf,0x3937384d,0xbbeabbab,0xb0a6b48d,0xb85ab943,0x3ab63a07,0xbbecbc00,0x30749a48,0xb493b6b5,0x3bab3b43,
0xba8cb9cb,0xb899b984,0xbab3bb46,0x385f36aa,0xbb9cbb28,0xb4f3b726,0xb91fb9fa,0x3a253951,0xbc00bbe4,0xa452b147,0xb631b828,0x3b603ad6,
0xbbb0bbee,0x346f3036,0xae5fb3df,0x3bf63bc1,0xbafeba4f,0xb7c8b8ec,0xb9f4bab5,0x3958385d,0xbbd8bb82,0xb24bb587,0xb80ab90e,0x3ae83a33,
0xbbf3bbfe,0x2f27a97f,0xb2f7b5da,0x3bcf3b72,0xbb4cbbb7,0x368d3438,0x2dc9ac1f,0x3bf83bfc,0xbb5cbac2,0xb648b848,0xb911b9fe,0x3a31394d,
0xbbf9bbc4,0xad33b3ae,0xb5b1b802,0x3b7a3aed,0xbbc5bbf9,0x33a22d1a,0xa94db26f,0x3bfe3bd6,0xbac4bb5d,0x38453642,0x346f2fa4,0x3bb03bf1,
0xbba5bb25,0xb4b7b732,0xb80fb927,0x3ae53a1f,0xbbffbbee,0x2884b036,0xb24bb5b6,0x3bd83b79,0xbb76bbd6,0x35c8326f,0x305ba7da,0x3bed3bff,
0xba19bae0,0x392e3817,0x374234c9,0x3b213ba2,0xbbd9bb77,0xb232b5c2,0xb5ebb832,0x3b6f3ad0,0xbbe8bc00,0x30d7a57f,0xa81fb288,0x3bff3bd5,
0xbb07bb95,0x37a6351d,0x34f33080,0x3b9c3bec,0xb94fba43,0x39fc38fb,0x38ea3780,0x3a503b11,0xbbf8bbb6,0xadc9b444,0xb328b64e,0x3bcc3b5a,
0xbbb7bbf8,0x343e2db0,0x3042a9e3,0x3bee3bfe,0xba7abb36,0x38b236ee,0x379034ed,0x3b0d3b9d,0xb86ab989,0x3aac39c7,0x3a0438fb,0x39463a43,
0xbc00bbe2,0x2311b179,0xac9cb414,0x3bfb3bbc,0xbb6abbd7,0x36023257,0x34b72f40,0x3ba53bf3,0xb9d2babc,0x397d3852,0x38f83775,0x3a453b14,
0xb6ddb8b5,0x3b3a3a78,0x3ae83a0b,0x380a393e,0xbbf2bbfa,0x2f8bacb5,0x2d33af0e,0x3bf93bf4,0xbb04bb9e,0x37b234e1,0x372c3451,0x3b273bb4,
0xb911ba27,0x3a31391d,0x3a0038e2,0x394a3a56,0xb4c3b796,0x3ba33b0b,0x3b8b3ae6,0x3552380d,0x4c004c00,0x26480000,0x4c004c00,0x33113248,
0x4c004c00,0x2cb62a48,0x4c004c00,0x345233db,0x4c004c00,0x2fdb2e48,0x4c004c00,0x351b34b6,0x4c004c00,0x317f30b6,0x4bff4c00,0x35e4357f,
0x4c004c00,0x2fdb0000,0x4bfb4bfc,0x3c6a3bd9,0x4bff4c00,0x35e433db,0x4bf94bfa,0x3d653ce7,0x4bfe4bff,0x38e837da,0x4bf64bf7,0x3e5f3de2,
0x4bfd4bfe,0x3ade39e3,0x4bf24bf4,0x3f593edc,0x4c004c00,0x33110000,0x4bf04bf4,0x3fef3f0e,0x4bfe4bff,0x394d3711,0x4be84bed,0x40d74067,
0x4bfb4bfd,0x3c6a3b11,0x4bdf4be4,0x41b64147,0x4bf64bf9,0x3e2d3d4c,0x4bd44bda,0x42944226,0x4c004c00,0x351b0000,0x4bdf4be6,0x41b64115,
0x4bfc4bfe,0x3ba7391b,0x4bcf4bd7,0x42f74257,0x4bf64bf9,0x3e5f3d1a,0x4bbc4bc6,0x441a4396,0x4bec4bf1,0x40743fa4,0x4ba54bb1,0x44b74469,
0x4bff4c00,0x36ad0000,0x4bc84bd4,0x437142a1,0x4bfa4bfd,0x3d003aac,0x4bac4bbb,0x44874420,0x4bef4bf5,0x40293eaa,0x4b8b4b9d,0x455244ed,
0x4bde4be7,0x41cf40fd,0x4b654b79,0x461a45b6,0x4bff4c00,0x381f0000,0x4bab4bbc,0x44934414,0x4bf64bfc,0x3e2d3c1f,0x4b814b97,0x458d4511,
0x4be54bef,0x4122401d,0x4b4f4b69,0x46824608,0x4bcc4bda,0x43284226,0x4b164b33,0x476f46f9,0x4bfe4c00,0x38e80000,0x4b874ba0,0x456a44d5,
0x4bf24bfa,0x3f593ce7,0x4b4c4b6b,0x468d45fd,0x4bda4be8,0x421940e4,0x4b074b2b,0x47a6471b,0x4bb74bca,0x443e434c,0x4ab64ae0,0x485a4817,
0x4bfe4c00,0x39b10000,0x4b5e4b80,0x463c4593,0x4bee4bf8,0x40423db0,0x4b104b39,0x478546e3,0x4bce4be0,0x430f41aa,0x4ab34ae3,0x485f4812,
0x4b9e4bb7,0x44e74438,0x4a494a7f,0x48f348ab,0x4bfd4c00,0x3a7a0000,0x4b2f4b5a,0x470a464e,0x4be84bf6,0x40d73e78,0x4acb4aff,0x483a47c2,
0x4bbf4bd6,0x4402426f,0x4a544a92,0x48e54891,0x4b814ba2,0x458d44c9,0x49cd4a13,0x49824935,0x4bfd4c00,0x3b430000,0x4afb4b30,0x47d24705,
0x4be24bf3,0x416c3f40,0x4a7e4abf,0x48ad484d,0x4bae4bcb,0x447b4334,0x49eb4a37,0x49624909,0x4b604b8a,0x46314558,0x4946499b,0x4a0449b5,
0x4bfc4c00,0x3c060000,0x4ac14b02,0x484a47b7,0x4bdc4bf0,0x42014004,0x4a294a78,0x491b48b5,0x4b9c4bc0,0x44f343f7,0x497949d4,0x49d6497b,
0x4b3d4b70,0x46d245e5,0x48b24918,0x4a7a4a2b,0x4bfb4c00,0x3c6a0000,0x4a814ad0,0x48a84832,0x4bd44bed,0x42944067,0x49cd4a2b,0x49824918,
0x4b874bb2,0x456a445d,0x48fd4969,0x4a4149e5,0x4b164b53,0x476f4670,0x4815488c,0x4ae14a95,0x4bfa4c00,0x3cce0000,0x4a3d4a99,0x49024887,
0x4bcc4be9,0x432840cb,0x496b49d8,0x49e34976,0x4b714ba4,0x45df44bd,0x487a48f6,0x4aa24a47,0x4aeb4b33,0x480546f9,0x46dd47ee,0x4b3a4af3,
0x4bf94c00,0x3d330000,0x49f44a5e,0x495848d8,0x4bc34be5,0x43ba412e,0x49024980,0x4a3d49d0,0x4b594b95,0x4654451d,0x47dd487c,0x4af74aa0,
0x4abd4b11,0x48504780,0x458146b5,0x4b834b43,0x4bf84c00,0x3d970000,0x49a64a1f,0x49aa4927,0x4bba4be1,0x44264191,0x48944922,0x4a904a23,
0x4b3f4b84,0x46c6457c,0x46bb47f9,0x4b424af0,0x4a8c4aed,0x48994802,0x441a4570,0x4bbc4b86,0x4bf74c00,0x3dfb0000,0x495449dc,0x49f84972,
0x4bb04bdc,0x446f41f4,0x482048bf,0x4adb4a71,0x4b244b72,0x473745da,0x458d46ee,0x4b814b36,0x4a584ac6,0x48e04842,0x41534420,0x4be34bbb,
0x4bf64c00,0x3e5f0000,0x48fd4996,0x4a4149ba,0x4ba54bd7,0x44b74257,0x474e4858,0x4b1e4ab8,0x4b074b5f,0x47a64637,0x445745da,0x4bb34b72,
0x4a214a9c,0x49244881,0x3cce4191,0x4bfa4be1,0x4bf54c00,0x3ec30000,0x48a3494d,0x4a8549fe,0x4b9a4bd2,0x44ff42b9,0x465447d8,0x4b594af9,
0x4ae84b4b,0x480a4693,0x423244bd,0x4bd94ba4,0x49e74a71,0x496648bf,0xb4523db0,0x4c004bf8,0x4bf34c00,0x3f270000,0x48454900,0x4ac44a3f,
0x4b8e4bcd,0x4546431b,0x455246f9,0x4b8b4b33,0x4ac74b36,0x484046ee,0x3f594334,0x4bf24bcb,0x49aa4a43,0x49a648fb,0xbef52a48,0x4bf44c00,
0x4bf24c00,0x3f8b0000,0x47c848b0,0x4afe4a7c,0x4b814bc7,0x458d437d,0x444b4614,0x4bb54b67,0x4aa54b20,0x48744748,0x388440e4,0x4bff4be8,
0x496b4a13,0x49e34935,0xc263bd4c,0x4bd74bf9,0x4bf04c00,0x3fef0000,0x46ff485d,0x4b324ab5,0x4b734bc1,0x45d443df,0x427c4529,0x4bd64b93,
0x4a814b08,0x48a847a1,0xb9b13d1a,0x4bfe4bf9,0x492949e1,0x4a1d496d,0xc49fc160,0x4ba94be3,0x4bef4c00,0x40290000,0x46314807,0x4b604ae9,
0x4b654bbb,0x461a4420,0x405b4438,0x4bed4bb7,0x4a5c4af0,0x48db47f9,0xbfef2e48,0x4bf04c00,0x48e549ad,0x4a5449a4,0xc602c408,0x4b6a4bbe,
0x4bed4c00,0x405b0000,0x455e475e,0x4b894b1a,0x4b574bb4,0x465f4451,0x3c6a4288,0x4bfb4bd5,0x4a354ad6,0x490c4828,0xc27cbc51,0x4bd64bfb,
0x489e4976,0x4a8949d8,0xc759c558,0x4b1b4b8a,0x4beb4c00,0x408d0000,0x448746aa,0x4bac4b46,0x4b474bad,0x46a44481,0x26484099,0x4c004beb,
0x4a0d4abc,0x493c4852,0xc47bc080,0x4bae4bec,0x4855493e,0x4aba4a0b,0xc850c69e,0x4abd4b49,0x4be94c00,0x40be0000,0x435945f1,0x4bc94b6e,
0x4b374ba6,0x46e844b1,0xbc383d4c,0x4bfc4bf9,0x49e34aa0,0x496b487c,0xc5b1c2d2,0x4b7a4bd1,0x480a4905,0x4ae84a3b,0xc8eac7d8,0x4a504af9,
0x4be74c00,0x40f00000,0x419e4534,0x4be04b91,0x4b274b9e,0x472c44e1,0xc042357f,0x4bee4c00,0x49b84a83,0x499948a6,0xc6ddc48d,0x4b3a4bab,
0x477a48c9,0x4b134a69,0xc979c881,0x49d64a9c,0x4be54c00,0x41220000,0x3fbd4475,0x4bf14baf,0x4b164b97,0x476f4511,0xc263b91b,0x4bd74bfe,
0x498b4a65,0x49c548ce,0xc7fec5ab,0x4aee4b7b,0x46dd488c,0x4b3a4a95,0xc9fcc90e,0x494f4a33,0x4be34c00,0x41530000,0x3c384365,0x4bfc4bc9,
0x4b044b8f,0x47b24540,0xc43ebe78,0x4bb74bf6,0x495d4a47,0x49f048f6,0xc889c6c1,0x4a974b41,0x463c484d,0x4b5e4abf,0xca73c992,0x48bc49be,
0x4be14c00,0x41850000,0x317f41db,0x4c004bdd,0x4af14b86,0x47f34570,0xc546c12e,0x4b8e4be5,0x492e4a27,0x4a19491d,0xc90cc7cd,0x4a354afc,
0x4599480d,0x4b7f4ae6,0xcadbca0b,0x4820493e,0x4bdf4c00,0x41b60000,0xb9b1404e,0x4bfe4bed,0x4ade4b7d,0x481a459f,0xc648c31b,0x4b5c4bcd,
0x48fd4a07,0x4a414943,0xc986c867,0x49c94aae,0x44f34796,0x4b9c4b0b,0xcb35ca78,0x46f448b5,0x4bdd4c00,0x41e80000,0xbe5f3d7e,0x4bf64bf8,
0x4acb4b74,0x483a45ce,0xc742c481,0x4b214bad,0x48cc49e5,0x4a674969,0xc9f8c8e2,0x49544a56,0x444b4710,0x4bb54b2e,0xcb7fcad9,0x45994822,
0x4bda4c00,0x42190000,0xc0f038b6,0x4be74bff,0x4ab64b6b,0x485a45fd,0xc81ac570,0x4ade4b86,0x489949c3,0x4a8c498d,0xca60c956,0x48d649f6,
0x43404687,0x4bcb4b4e,0xcbb8cb2e,0x44324710,0x4bd84c00,0x424b0000,0xc2adb248,0x4bd34c00,0x4aa24b62,0x487a462b,0xc88ec659,0x4a934b58,
0x4865499f,0x4ab049b1,0xcabdc9c3,0x4850498d,0x41e845fd,0x4bdd4b6b,0xcbe1cb74,0x418545ce,0x4bd64c00,0x427c0000,0xc432bbd9,0x4bb84bfc,
0x4a8c4b58,0x48994659,0xc8fdc73d,0x4a414b22,0x4830497b,0x4ad149d4,0xcb10ca27,0x4785491d,0x408d4570,0x4beb4b86,0xcbf9cbad,0x3d334481,
0x4bd34c00,0x42ad0000,0xc50bbf0e,0x4b984bf4,0x4a764b4e,0x48b74687,0xc966c80d,0x49e74ae6,0x47f34956,0x4af149f6,0xcb57ca83,0x465f48a6,
0x3e5f44e1,0x4bf64b9e,0xcc00cbd7,0xb17f4257,0x4bd04c00,0x42de0000,0xc5dfc115,0x4b714be6,0x4a604b43,0x48d646b5,0xc9c9c877,0x49864aa3,
0x47854930,0x4b104a17,0xcb92cad6,0x452f4828,0x3b434451,0x4bfd4bb4,0xcbf5cbf3,0xbe913f40,0x4bce4c00,0x430f0000,0xc6afc2a1,0x4b454bd4,
0x4a494b39,0x48f346e3,0xca25c8dd,0x491f4a5a,0x47154909,0x4b2c4a37,0xcbc0cb20,0x43eb4748,0x3311437d,0x4c004bc7,0xcbd9cbff,0xc2323711,
0x4bcb4c00,0x43400000,0xc77ac414,0x4b134bbc,0x4a314b2e,0x49114710,0xca7ac93e,0x48b24a0b,0x46a448e2,0x4b474a56,0xcbe2cb5f,0x416c4637,
0xb7764257,0x4bff4bd7,0xcbaccbfd,0xc487bb75,0x4bc84c00,0x43710000,0xc820c4d5,0x4adb4ba0,0x4a194b22,0x492e473d,0xcac7c99b,0x484049b5,
0x463148ba,0x4b604a74,0xcbf8cb95,0x3dc9451d,0xbc9c412e,0x4bfb4be5,0xcb6fcbeb,0xc5ebc099,0x4bc54c00,0x43a20000,0xc87fc593,0x4a9e4b80,
0x4a004b17,0x494a476a,0xcb0dc9f2,0x4790495b,0x45bc4891,0x4b784a92,0xcc00cbc0,0x317f43f7,0xbf594004,0x4bf24bf0,0xcb21cbca,0xc742c34c,
0x4bc24c00,0x43d30000,0xc8dbc64e,0x4a5c4b5a,0x49e74b0b,0x49664796,0xcb4aca43,0x469948fb,0x45464867,0x4b8e4aae,0xcbfbcbe0,0xbc6a41aa,
0xc1093db0,0x4be64bf8,0xcac4cb9b,0xc845c4f9,0x4bbf4c00,0x44020000,0xc933c705,0x4a154b30,0x49cd4aff,0x498247c2,0xcb7fca8e,0x45994896,
0x44cf483d,0x4ba14ac9,0xcbe9cbf5,0xc0be3eaa,0xc2633aac,0x4bd74bfd,0xca58cb5d,0xc8e0c642,0x4bbc4c00,0x441a0000,0xc986c7b7,0x49c94b02,
0x49b34af3,0x499d47ee,0xcbabcad3,0x4493482d,0x44574812,0x4bb34ae3,0xcbcbcbff,0xc34037da,0xc3ba33db,0x4bc34c00,0xc9dfcb11,0xc970c780,
0x4bb84c00,0x44320000,0xc9d6c832,0x49794ad0,0x49994ae6,0x49b8480d,0xcbcecb11,0x430f4780,0x43ba47cd,0x4bc34afc,0xcb9fcbfe,0xc4dbb97f,
0xc487b57f,0x4bac4c00,0xc958cab8,0xc9f4c858,0x4bb54c00,0x444b0000,0xca21c887,0x49244a99,0x497d4ad9,0x49d24822,0xcbe7cb49,0x40f0469e,
0x42c64775,0x4bd24b14,0xcb68cbf2,0xc60ebf72,0xc52fbb75,0x4b924bfd,0xc8c7ca52,0xca6bc8e7,0x4bb24c00,0x44630000,0xca67c8d8,0x48cc4a5e,
0x49624acc,0x49eb4838,0xcbf8cb79,0x3d9745b6,0x41cf471b,0x4bde4b2b,0xcb24cbdb,0xc737c20d,0xc5d4be14,0x4b734bf7,0xc82ac9e1,0xcad5c96d,
0x4bae4c00,0x447b0000,0xcaa9c927,0x486f4a1f,0x49464abf,0x4a04484d,0xcc00cba2,0x351b44c9,0x40d746c1,0x4be84b41,0xcad5cbb9,0xc82ac42c,
0xc676c036,0x4b524bee,0xc70ac964,0xcb2fc9e9,0x4bab4c00,0x44930000,0xcae5c972,0x480f49dc,0x49294ab1,0x4a1d4862,0xcbfecbc4,0xba1643ae,
0x3fbd4665,0x4bf14b55,0xca7acb8c,0xc8b2c54c,0xc715c160,0x4b2c4be3,0xc5b1c8dd,0xcb7aca5a,0x4ba74c00,0x44ab0000,0xcb1bc9ba,0x47594996,
0x490c4aa3,0x4a354877,0xcbf2cbdf,0xbf5941c3,0x3dc94608,0x4bf84b69,0xca15cb55,0xc933c665,0xc7b2c288,0x4b044bd5,0xc44bc84d,0xcbb5cabf,
0x4ba34c00,0x44c30000,0xcb4cc9fe,0x468d494d,0x48ee4a95,0x4a4d488c,0xcbdecbf1,0xc1cf3fa4,0x3ba745ab,0x4bfc4b7b,0xc9a6cb14,0xc9aac775,
0xc825c3ae,0x4ad84bc4,0xc1b6c76a,0xcbdfcb17,0x4b9f4c00,0x44db0000,0xcb78ca3f,0x45bc4900,0x48d14a87,0x4a6448a0,0xcbc0cbfd,0xc3eb3b75,
0x3776454c,0x4bff4b8c,0xc92ecac9,0xca19c83d,0xc86fc469,0x4aa94bb1,0xbd97c62b,0xcbf8cb62,0x4b9c4c00,0x44f30000,0xcb9eca7c,0x44e748b0,
0x48b24a78,0x4a7a48b5,0xcb9acc00,0xc4ffaa48,0xa64844ed,0x4c004b9d,0xc8adca74,0xca7ec8ba,0xc8b7c4f9,0x4a764b9b,0x2cb6c4e1,0xcc00cb9e,
0x4b984c00,0x450b0000,0xcbbdcab5,0x440e485d,0x48944a69,0x4a9048c9,0xcb6acbfc,0xc602bc1f,0xb81f448d,0x4bff4bab,0xc825ca17,0xcad8c930,
0xc8fdc587,0x4a414b82,0x3e2dc31b,0xcbf6cbcd,0x4b944c00,0x45230000,0xcbd7cae9,0x42634807,0x48744a5a,0x4aa548dd,0xcb32cbf0,0xc6ffc004,
0xbc06442c,0x4bfc4bb9,0xc72cc9b1,0xcb27c99f,0xc941c614,0x4a094b67,0x4201c067,0xcbdccbed,0x4b904c00,0x453a0000,0xcbeacb1a,0x40a6475e,
0x48554a4b,0x4aba48f1,0xcaf1cbdc,0xc7f3c1f4,0xbdfb4396,0x4bf74bc6,0xc602c943,0xcb6aca07,0xc982c69e,0x49cd4b49,0x446fbaac,0xcbb0cbfd,
0x4b8b4c00,0x45520000,0xcbf8cb46,0x3dc946aa,0x48354a3b,0x4ace4905,0xcaa9cbc1,0xc86fc3df,0xbfef42d2,0x4bf04bd1,0xc4cfc8ce,0xcba1ca65,
0xc9c0c726,0x49904b28,0x45d43852,0xcb73cbff,0x4b874c00,0x456a0000,0xcbffcb6e,0x388445f1,0x48154a2b,0x4ae14918,0xca58cb9e,0xc8e0c4e1,
0xc0f0420d,0x4be74bdb,0xc328c852,0xcbcccabc,0xc9fcc7ac,0x494f4b05,0x472c3fa4,0xcb27cbf1,0x4b834c00,0x45810000,0xcc00cb91,0xb51b4534,
0x47e84a1b,0x4af4492b,0xca00cb74,0xc94ac5ce,0xc1e84147,0x4bdd4be4,0xc0a6c7a1,0xcbeacb08,0xca35c817,0x490c4ae0,0x483a4288,0xcacbcbd5,
0x4b7f4c00,0x45990000,0xcbfacbaf,0xbcce4475,0x47a64a0b,0x4b07493e,0xc9a1cb43,0xc9afc6b5,0xc2de4080,0x4bd04bec,0xbc38c693,0xcbfccb4b,
0xca6bc858,0x48c74ab8,0x48d64499,0xca60cbaa,0x4b7a4c00,0x45b10000,0xcbefcbc9,0xc0294365,0x476449fa,0x4b184951,0xc93ccb0b,0xca0dc796,
0xc3d33f72,0x4bc24bf2,0x3311c57c,0xcc00cb84,0xca9ec896,0x487f4a8e,0x496645e5,0xc9e7cb70,0x4b764c00,0x45c80000,0xcbddcbdd,0xc1e841db,
0x472149e9,0x4b2a4964,0xc8d1cacc,0xca64c838,0xc4633de2,0x4bb24bf7,0x3dfbc45d,0xcbf7cbb2,0xcacec8d3,0x48354a62,0x49eb4726,0xc962cb28,
0x4b714c00,0x45df0000,0xcbc5cbed,0xc3a2404e,0x46dd49d8,0x4b3a4976,0xc85fca87,0xcab3c8a0,0xc4db3c51,0x4b9f4bfb,0x4185c26f,0xcbe1cbd6,
0xcafbc90e,0x47d24a33,0x4a64482d,0xc8d1cad3,0x4b6c4c00,0x45f70000,0xcba7cbf8,0xc4ab3d7e,0x469949c7,0x4b4a4989,0xc7d2ca3b,0xcafbc905,
0xc552397f,0x4b8b4bfe,0x4402c01d,0xcbbfcbef,0xcb24c948,0x47374a02,0x4ace48bf,0xc835ca71,0x4b684c00,0x460e0000,0xcb83cbff,0xc58138b6,
0x465449b5,0x4b59499b,0xc6ddc9e9,0xcb3ac964,0xc5c834b6,0x4b764c00,0x453abb11,0xcb90cbfd,0xcb4ac980,0x469949d0,0x4b2a4948,0xc721ca02,
0x2c002c00,0x2c002c00,0x2c002c00,0x2c002c00,0x2b642c00,0x261f29a8,0xa61f0000,0xab64a9a8,0x29a82c00,0xa9a80000,0xa9a8ac00,0x29a80000,
0x261f2c00,0xab64a9a8,0x2b640000,0xa61f29a8,0x2c00,0xac00,0x2c00,0xac00,0xa61f2c00,0x2b64a9a8,0xab640000,0x261f29a8,
0xa9a82c00,0x29a80000,0x29a8ac00,0xa9a80000,0xab642c00,0xa61f29a8,0x261f0000,0x2b64a9a8,0,0,0,0,
0x261f0000,0x2b6429a8,0x2b642c00,0x261f29a8,0x29a80000,0x29a82c00,0xa9a80000,0xa9a8ac00,0x2b640000,0xa61f29a8,0xa61fac00,0x2b6429a8,
0x2c000000,0xac000000,0x2c000000,0xac000000,0x2b640000,0xa61fa9a8,0xa61f2c00,0x2b64a9a8,0x29a80000,0x29a8ac00,0xa9a80000,0xa9a82c00,
0x261f0000,0x2b64a9a8,0x2b64ac00,0x261fa9a8,0xac002c00,0xac002c00,0xac002c00,0xac002c00,0xab642c00,0xa61f29a8,0x261f0000,0x2b64a9a8,
0xa9a82c00,0x29a80000,0x29a8ac00,0xa9a80000,0xa61f2c00,0x2b64a9a8,0xab640000,0x261f29a8,0x2c00,0xac00,0x2c00,0xac00,
0x261f2c00,0xab64a9a8,0x2b640000,0xa61f29a8,0x29a82c00,0xa9a80000,0xa9a8ac00,0x29a80000,0x2b642c00,0x261f29a8,0xa61f0000,0xab64a9a8,
0,0,0,0,0xa61f0000,0xab6429a8,0xab642c00,0xa61f29a8,0xa9a80000,0xa9a82c00,0x29a80000,0x29a8ac00,
0xab640000,0x261f29a8,0x261fac00,0xab6429a8,0xac000000,0x2c000000,0xac000000,0x2c000000,0xab640000,0x261fa9a8,0x261f2c00,0xab64a9a8,
0xa9a80000,0xa9a8ac00,0x29a80000,0x29a82c00,0xa61f0000,0xab64a9a8,0xab64ac00,0xa61fa9a8,0,0,0,0,
0xa61f0000,0xab64a9a8,0xab64ac00,0xa61fa9a8,0xa9a80000,0xa9a8ac00,0x29a80000,0x29a82c00,0xab640000,0x261fa9a8,0x261f2c00,0xab64a9a8,
0xac000000,0x2c000000,0xac000000,0x2c000000,0xab640000,0x261f29a8,0x261fac00,0xab6429a8,0xa9a80000,0xa9a82c00,0x29a80000,0x29a8ac00,
0xa61f0000,0xab6429a8,0xab642c00,0xa61f29a8,0x2c002c00,0x2c002c00,0x2c002c00,0x2c002c00,0x2b642c00,0x261f29a8,0xa61f0000,0xab64a9a8,
0x29a82c00,0xa9a80000,0xa9a8ac00,0x29a80000,0x261f2c00,0xab64a9a8,0x2b640000,0xa61f29a8,0x2c00,0xac00,0x2c00,0xac00,
0xa61f2c00,0x2b64a9a8,0xab640000,0x261f29a8,0xa9a82c00,0x29a80000,0x29a8ac00,0xa9a80000,0xab642c00,0xa61f29a8,0x261f0000,0x2b64a9a8,
0,0,0,0,0x261f0000,0x2b64a9a8,0x2b64ac00,0x261fa9a8,0x29a80000,0x29a8ac00,0xa9a80000,0xa9a82c00,
0x2b640000,0xa61fa9a8,0xa61f2c00,0x2b64a9a8,0x2c000000,0xac000000,0x2c000000,0xac000000,0x2b640000,0xa61f29a8,0xa61fac00,0x2b6429a8,
0x29a80000,0x29a82c00,0xa9a80000,0xa9a8ac00,0x261f0000,0x2b6429a8,0x2b642c00,0x261f29a8,0xac002c00,0xac002c00,0xac002c00,0xac002c00,
0xab642c00,0xa61f29a8,0x261f0000,0x2b64a9a8,0xa9a82c00,0x29a80000,0x29a8ac00,0xa9a80000,0xa61f2c00,0x2b64a9a8,0xab640000,0x261f29a8,
0x2c00,0xac00,0x2c00,0xac00,0x261f2c00,0xab64a9a8,0x2b640000,0xa61f29a8,0x29a82c00,0xa9a80000,0xa9a8ac00,0x29a80000,
0x2b642c00,0x261f29a8,0xa61f0000,0xab64a9a8,0x2c002c00,0x2c002c00,0x2c002c00,0x2c002c00,0xab64ac00,0xa61fa9a8,0x261f0000,0x2b6429a8,
0x29a82c00,0xa9a80000,0xa9a8ac00,0x29a80000,0xa61fac00,0x2b6429a8,0xab640000,0x261fa9a8,0x2c00,0xac00,0x2c00,0xac00,
0x261fac00,0xab6429a8,0x2b640000,0xa61fa9a8,0xa9a82c00,0x29a80000,0x29a8ac00,0xa9a80000,0x2b64ac00,0x261fa9a8,0xa61f0000,0xab6429a8,
0,0,0,0,0xa61f0000,0xab64a9a8,0xab64ac00,0xa61fa9a8,0x29a80000,0x29a82c00,0xa9a80000,0xa9a8ac00,
0xab640000,0x261fa9a8,0x261f2c00,0xab64a9a8,0x2c000000,0xac000000,0x2c000000,0xac000000,0xab640000,0x261f29a8,0x261fac00,0xab6429a8,
0x29a80000,0x29a8ac00,0xa9a80000,0xa9a82c00,0xa61f0000,0xab6429a8,0xab642c00,0xa61f29a8,0xac002c00,0xac002c00,0xac002c00,0xac002c00,
0x2b64ac00,0x261fa9a8,0xa61f0000,0xab6429a8,0xa9a82c00,0x29a80000,0x29a8ac00,0xa9a80000,0x261fac00,0xab6429a8,0x2b640000,0xa61fa9a8,
0x2c00,0xac00,0x2c00,0xac00,0xa61fac00,0x2b6429a8,0xab640000,0x261fa9a8,0x29a82c00,0xa9a80000,0xa9a8ac00,0x29a80000,
0xab64ac00,0xa61fa9a8,0x261f0000,0x2b6429a8,0,0,0,0,0x261f0000,0x2b64a9a8,0x2b64ac00,0x261fa9a8,
0xa9a80000,0xa9a82c00,0x29a80000,0x29a8ac00,0x2b640000,0xa61fa9a8,0xa61f2c00,0x2b64a9a8,0xac000000,0x2c000000,0xac000000,0x2c000000,
0x2b640000,0xa61f29a8,0xa61fac00,0x2b6429a8,0xa9a80000,0xa9a8ac00,0x29a80000,0x29a82c00,0x261f0000,0x2b6429a8,0x2b642c00,0x261f29a8,
0,0,0,0,0x261f0000,0x2b6429a8,0x2b642c00,0x261f29a8,0xa9a80000,0xa9a8ac00,0x29a80000,0x29a82c00,
0x2b640000,0xa61f29a8,0xa61fac00,0x2b6429a8,0xac000000,0x2c000000,0xac000000,0x2c000000,0x2b640000,0xa61fa9a8,0xa61f2c00,0x2b64a9a8,
0xa9a80000,0xa9a82c00,0x29a80000,0x29a8ac00,0x261f0000,0x2b64a9a8,0x2b64ac00,0x261fa9a8,0x2c002c00,0x2c002c00,0x2c002c00,0x2c002c00,
0xab64ac00,0xa61fa9a8,0x261f0000,0x2b6429a8,0x29a82c00,0xa9a80000,0xa9a8ac00,0x29a80000,0xa61fac00,0x2b6429a8,0xab640000,0x261fa9a8,
0x2c00,0xac00,0x2c00,0xac00,0x261fac00,0xab6429a8,0x2b640000,0xa61fa9a8,0xa9a82c00,0x29a80000,0x29a8ac00,0xa9a80000,
0x2b64ac00,0x261fa9a8,0xa61f0000,0xab6429a8,0,0,0,0,0xa61f0000,0xab6429a8,0xab642c00,0xa61f29a8,
0x29a80000,0x29a8ac00,0xa9a80000,0xa9a82c00,0xab640000,0x261f29a8,0x261fac00,0xab6429a8,0x2c000000,0xac000000,0x2c000000,0xac000000,
0xab640000,0x261fa9a8,0x261f2c00,0xab64a9a8,0x29a80000,0x29a82c00,0xa9a80000,0xa9a8ac00,0xa61f0000,0xab64a9a8,0xab64ac00,0xa61fa9a8,
0xac002c00,0xac002c00,0xac002c00,0xac002c00,0x2b64ac00,0x261fa9a8,0xa61f0000,0xab6429a8,0xa9a82c00,0x29a80000,0x29a8ac00,0xa9a80000,
0x261fac00,0xab6429a8,0x2b640000,0xa61fa9a8,0x2c00,0xac00,0x2c00,0xac00,0xa61fac00,0x2b6429a8,0xab640000,0x261fa9a8,
0x29a82c00,0xa9a80000,0xa9a8ac00,0x29a80000,0xab64ac00,0xa61fa9a8,0x261f0000,0x2b6429a8,0x2bd92c00,0x2aa72b64,0x287229a8,0x223e261f,
0x2aa72c00,0xa23e261f,0xabd9a9a8,0xa872ab64,0x28722c00,0xabd9a61f,0x223ea9a8,0x2aa72b64,0x223e2c00,0xa872ab64,0x2aa729a8,0xabd9a61f,
0xa23e2c00,0x2872ab64,0xaaa729a8,0x2bd9a61f,0xa8722c00,0x2bd9a61f,0xa23ea9a8,0xaaa72b64,0xaaa72c00,0x223e261f,0x2bd9a9a8,0x2872ab64,
0xabd92c00,0xaaa72b64,0xa87229a8,0xa23e261f,0x223e0000,0x2872261f,0x2aa729a8,0x2bd92b64,0x28720000,0x2bd92b64,0x223e29a8,0xaaa7a61f,
0x2aa70000,0x223e2b64,0xabd9a9a8,0x2872a61f,0x2bd90000,0xaaa7261f,0x2872a9a8,0xa23e2b64,0x2bd90000,0xaaa7a61f,0x287229a8,0xa23eab64,
0x2aa70000,0x223eab64,0xabd929a8,0x2872261f,0x28720000,0x2bd9ab64,0x223ea9a8,0xaaa7261f,0x223e0000,0x2872a61f,0x2aa7a9a8,0x2bd9ab64,
0xabd92c00,0xaaa72b64,0xa87229a8,0xa23e261f,0xaaa72c00,0x223e261f,0x2bd9a9a8,0x2872ab64,0xa8722c00,0x2bd9a61f,0xa23ea9a8,0xaaa72b64,
0xa23e2c00,0x2872ab64,0xaaa729a8,0x2bd9a61f,0x223e2c00,0xa872ab64,0x2aa729a8,0xabd9a61f,0x28722c00,0xabd9a61f,0x223ea9a8,0x2aa72b64,
0x2aa72c00,0xa23e261f,0xabd9a9a8,0xa872ab64,0x2bd92c00,0x2aa72b64,0x287229a8,0x223e261f,0xa23e0000,0xa872261f,0xaaa729a8,0xabd92b64,
0xa8720000,0xabd92b64,0xa23e29a8,0x2aa7a61f,0xaaa70000,0xa23e2b64,0x2bd9a9a8,0xa872a61f,0xabd90000,0x2aa7261f,0xa872a9a8,0x223e2b64,
0xabd90000,0x2aa7a61f,0xa87229a8,0x223eab64,0xaaa70000,0xa23eab64,0x2bd929a8,0xa872261f,0xa8720000,0xabd9ab64,0xa23ea9a8,0x2aa7261f,
0xa23e0000,0xa872a61f,0xaaa7a9a8,0xabd9ab64,0xa23e0000,0xa872a61f,0xaaa7a9a8,0xabd9ab64,0xa8720000,0xabd9ab64,0xa23ea9a8,0x2aa7261f,
0xaaa70000,0xa23eab64,0x2bd929a8,0xa872261f,0xabd90000,0x2aa7a61f,0xa87229a8,0x223eab64,0xabd90000,0x2aa7261f,0xa872a9a8,0x223e2b64,
0xaaa70000,0xa23e2b64,0x2bd9a9a8,0xa872a61f,0xa8720000,0xabd92b64,0xa23e29a8,0x2aa7a61f,0xa23e0000,0xa872261f,0xaaa729a8,0xabd92b64,
0x2bd92c00,0x2aa72b64,0x287229a8,0x223e261f,0x2aa72c00,0xa23e261f,0xabd9a9a8,0xa872ab64,0x28722c00,0xabd9a61f,0x223ea9a8,0x2aa72b64,
0x223e2c00,0xa872ab64,0x2aa729a8,0xabd9a61f,0xa23e2c00,0x2872ab64,0xaaa729a8,0x2bd9a61f,0xa8722c00,0x2bd9a61f,0xa23ea9a8,0xaaa72b64,
0xaaa72c00,0x223e261f,0x2bd9a9a8,0x2872ab64,0xabd92c00,0xaaa72b64,0xa87229a8,0xa23e261f,0x223e0000,0x2872a61f,0x2aa7a9a8,0x2bd9ab64,
0x28720000,0x2bd9ab64,0x223ea9a8,0xaaa7261f,0x2aa70000,0x223eab64,0xabd929a8,0x2872261f,0x2bd90000,0xaaa7a61f,0x287229a8,0xa23eab64,
0x2bd90000,0xaaa7261f,0x2872a9a8,0xa23e2b64,0x2aa70000,0x223e2b64,0xabd9a9a8,0x2872a61f,0x28720000,0x2bd92b64,0x223e29a8,0xaaa7a61f,
0x223e0000,0x2872261f,0x2aa729a8,0x2bd92b64,0xabd92c00,0xaaa72b64,0xa87229a8,0xa23e261f,0xaaa72c00,0x223e261f,0x2bd9a9a8,0x2872ab64,
0xa8722c00,0x2bd9a61f,0xa23ea9a8,0xaaa72b64,0xa23e2c00,0x2872ab64,0xaaa729a8,0x2bd9a61f,0x223e2c00,0xa872ab64,0x2aa729a8,0xabd9a61f,
0x28722c00,0xabd9a61f,0x223ea9a8,0x2aa72b64,0x2aa72c00,0xa23e261f,0xabd9a9a8,0xa872ab64,0x2bd92c00,0x2aa72b64,0x287229a8,0x223e261f,
0xa23e0000,0xa872a61f,0xaaa7a9a8,0xabd9ab64,0x28720000,0x2bd92b64,0x223e29a8,0xaaa7a61f,0xaaa70000,0xa23eab64,0x2bd929a8,0xa872261f,
0x2bd90000,0xaaa7261f,0x2872a9a8,0xa23e2b64,0xabd90000,0x2aa7261f,0xa872a9a8,0x223e2b64,0x2aa70000,0x223eab64,0xabd929a8,0x2872261f,
0xa8720000,0xabd92b64,0xa23e29a8,0x2aa7a61f,0x223e0000,0x2872a61f,0x2aa7a9a8,0x2bd9ab64,0x2bd92c00,0x2aa72b64,0x287229a8,0x223e261f,
0xaaa7ac00,0x223ea61f,0x2bd929a8,0x28722b64,0x28722c00,0xabd9a61f,0x223ea9a8,0x2aa72b64,0xa23eac00,0x28722b64,0xaaa7a9a8,0x2bd9261f,
0xa23e2c00,0x2872ab64,0xaaa729a8,0x2bd9a61f,0x2872ac00,0xabd9261f,0x223e29a8,0x2aa7ab64,0xaaa72c00,0x223e261f,0x2bd9a9a8,0x2872ab64,
0x2bd9ac00,0x2aa7ab64,0x2872a9a8,0x223ea61f,0x223e0000,0x2872a61f,0x2aa7a9a8,0x2bd9ab64,0xa8720000,0xabd92b64,0xa23e29a8,0x2aa7a61f,
0x2aa70000,0x223eab64,0xabd929a8,0x2872261f,0xabd90000,0x2aa7261f,0xa872a9a8,0x223e2b64,0x2bd90000,0xaaa7261f,0x2872a9a8,0xa23e2b64,
0xaaa70000,0xa23eab64,0x2bd929a8,0xa872261f,0x28720000,0x2bd92b64,0x223e29a8,0xaaa7a61f,0xa23e0000,0xa872a61f,0xaaa7a9a8,0xabd9ab64,
0xabd92c00,0xaaa72b64,0xa87229a8,0xa23e261f,0x2aa7ac00,0xa23ea61f,0xabd929a8,0xa8722b64,0xa8722c00,0x2bd9a61f,0xa23ea9a8,0xaaa72b64,
0x223eac00,0xa8722b64,0x2aa7a9a8,0xabd9261f,0x223e2c00,0xa872ab64,0x2aa729a8,0xabd9a61f,0xa872ac00,0x2bd9261f,0xa23e29a8,0xaaa7ab64,
0x2aa72c00,0xa23e261f,0xabd9a9a8,0xa872ab64,0xabd9ac00,0xaaa7ab64,0xa872a9a8,0xa23ea61f,0xabd9ac00,0xaaa7ab64,0xa872a9a8,0xa23ea61f,
0x2aa72c00,0xa23e261f,0xabd9a9a8,0xa872ab64,0xa872ac00,0x2bd9261f,0xa23e29a8,0xaaa7ab64,0x223e2c00,0xa872ab64,0x2aa729a8,0xabd9a61f,
0x223eac00,0xa8722b64,0x2aa7a9a8,0xabd9261f,0xa8722c00,0x2bd9a61f,0xa23ea9a8,0xaaa72b64,0x2aa7ac00,0xa23ea61f,0xabd929a8,0xa8722b64,
0xabd92c00,0xaaa72b64,0xa87229a8,0xa23e261f,0xa23e0000,0xa872a61f,0xaaa7a9a8,0xabd9ab64,0x28720000,0x2bd92b64,0x223e29a8,0xaaa7a61f,
0xaaa70000,0xa23eab64,0x2bd929a8,0xa872261f,0x2bd90000,0xaaa7261f,0x2872a9a8,0xa23e2b64,0xabd90000,0x2aa7261f,0xa872a9a8,0x223e2b64,
0x2aa70000,0x223eab64,0xabd929a8,0x2872261f,0xa8720000,0xabd92b64,0xa23e29a8,0x2aa7a61f,0x223e0000,0x2872a61f,0x2aa7a9a8,0x2bd9ab64,
0x2bd9ac00,0x2aa7ab64,0x2872a9a8,0x223ea61f,0xaaa72c00,0x223e261f,0x2bd9a9a8,0x2872ab64,0x2872ac00,0xabd9261f,0x223e29a8,0x2aa7ab64,
0xa23e2c00,0x2872ab64,0xaaa729a8,0x2bd9a61f,0xa23eac00,0x28722b64,0xaaa7a9a8,0x2bd9261f,0x28722c00,0xabd9a61f,0x223ea9a8,0x2aa72b64,
0xaaa7ac00,0x223ea61f,0x2bd929a8,0x28722b64,0x2bd92c00,0x2aa72b64,0x287229a8,0x223e261f,0x223e0000,0x2872a61f,0x2aa7a9a8,0x2bd9ab64,
0xa8720000,0xabd92b64,0xa23e29a8,0x2aa7a61f,0x2aa70000,0x223eab64,0xabd929a8,0x2872261f,0xabd90000,0x2aa7261f,0xa872a9a8,0x223e2b64,
0x2bd90000,0xaaa7261f,0x2872a9a8,0xa23e2b64,0xaaa70000,0xa23eab64,0x2bd929a8,0xa872261f,0x28720000,0x2bd92b64,0x223e29a8,0xaaa7a61f,
0xa23e0000,0xa872a61f,0xaaa7a9a8,0xabd9ab64,0x27fe2800,0x96480000,0x273b2764,0xa2d7a21f,0x27ea27f6,0x9cb29a46,0x26dd270e,0xa41da38b,
0x27c327d9,0x9fc69e3e,0x266d26a7,0xa4c4a472,0x278827a8,0xa164a0a5,0x25ed262f,0xa55fa513,0x27c32800,0x9fc60000,0xa4c4a21f,0xa66da764,
0x25ed270e,0xa55fa38b,0xa73ba62f,0xa2d7a513,0x21642472,0xa788a6a7,0xa7fea7d9,0x16489e3e,0x9cb21a46,0xa7eaa7f6,0xa6dda7a8,0x241d20a5,
0x273b2800,0xa2d70000,0xa55fa764,0x25ed221f,0x1fc62513,0xa7c3a62f,0x1cb2a0a5,0x27ea27a8,0xa4c49e3e,0xa66da7d9,0x26dd2472,0x241d26a7,
0xa7fea70e,0x9648a38b,0x278827f6,0xa1641a46,0x266d2800,0xa4c40000,0x26dd221f,0x241d2764,0xa16420a5,0xa788a7a8,0x25ed27f6,0xa55f9a46,
0xa7fea6a7,0x1648a472,0xa2d71e3e,0xa73ba7d9,0x9fc6a62f,0x27c32513,0xa7eaa70e,0x1cb2a38b,0x255f2800,0xa5ed0000,0x21642764,0xa788a21f,
0xa66d9a46,0xa4c4a7f6,0xa7c3a38b,0x9fc6a70e,0xa41da7d9,0x26dd1e3e,0x9cb2a6a7,0x27ea2472,0x273b20a5,0x22d727a8,0x27fe2513,0x1648262f,
0x241d2800,0xa6dd0000,0xa7eaa21f,0x9cb2a764,0xa7fea38b,0x9648a70e,0x2164a513,0x2788262f,0x22d7a472,0x273b26a7,0x255f27d9,0xa5ed1e3e,
0x24c427f6,0xa66d1a46,0xa7c3a0a5,0x9fc6a7a8,0x21642800,0xa7880000,0x1648a764,0x27fe221f,0xa6dda62f,0x241da513,0x24c427a8,0xa66d20a5,
0x27ea1e3e,0x1cb227d9,0xa7c3a472,0x1fc6a6a7,0xa55f238b,0xa5eda70e,0x273b9a46,0x22d727f6,0x1cb22800,0xa7ea0000,0x27c3221f,0x9fc62764,
0xa2d7a7a8,0x273ba0a5,0xa7fe9a46,0x9648a7f6,0x255f26a7,0xa5ed2472,0x27889e3e,0x216427d9,0xa6dda513,0x241da62f,0xa66d238b,0xa4c4a70e,
0x96482800,0xa7fe0000,0xa2d72764,0xa73ba21f,0x1cb2a7f6,0x27ea1a46,0x241da70e,0x26dd238b,0x9fc627d9,0xa7c39e3e,0xa4c426a7,0xa66da472,
0x2164a7a8,0x278820a5,0x255fa62f,0x25ed2513,0x9fc62800,0xa7c30000,0xa66da21f,0x24c4a764,0x255fa70e,0x25ed238b,0x22d7262f,0xa73b2513,
0xa7882472,0xa164a6a7,0x1648a7d9,0x27fe9e3e,0x27ea9a46,0x9cb227f6,0xa41d27a8,0xa6dda0a5,0xa2d72800,0xa73b0000,0x25eda764,0x255f221f,
0x27c3a513,0x1fc6262f,0xa7ea20a5,0x1cb2a7a8,0xa66d9e3e,0x24c4a7d9,0x241d2472,0xa6dd26a7,0x1648270e,0xa7fe238b,0x2164a7f6,0x27889a46,
0xa4c42800,0xa66d0000,0x241d221f,0xa6dd2764,0x2788a0a5,0xa16427a8,0x255fa7f6,0x25ed1a46,0x1648a6a7,0x27fea472,0xa73b1e3e,0x22d7a7d9,
0xa7c3262f,0x9fc6a513,0x9cb2270e,0xa7ea238b,0xa5ed2800,0xa55f0000,0xa7882764,0xa164a21f,0x24c41a46,0xa66d27f6,0x1fc6238b,0xa7c3270e,
0x26dda7d9,0x241d1e3e,0x27eaa6a7,0x1cb22472,0xa2d7a0a5,0x273ba7a8,0x9648a513,0x27fea62f,0xa6dd2800,0xa41d0000,0x9cb2a21f,0x27eaa764,
0x1648238b,0xa7fe270e,0xa7882513,0x2164a62f,0x273ba472,0xa2d726a7,0xa5ed27d9,0xa55f1e3e,0x266da7f6,0x24c49a46,0x1fc620a5,0xa7c327a8,
0xa7882800,0xa1640000,0x27fea764,0x9648221f,0xa41d262f,0xa6dd2513,0x266da7a8,0x24c4a0a5,0x1cb21e3e,0xa7ea27d9,0x1fc6a472,0x27c3a6a7,
0x25eda38b,0xa55f270e,0xa2d71a46,0x273ba7f6,0xa7ea2800,0x9cb20000,0x9fc6221f,0xa7c32764,0xa73b27a8,0xa2d720a5,0x16481a46,0xa7fe27f6,
0xa5ed26a7,0xa55f2472,0x21649e3e,0xa78827d9,0xa41d2513,0xa6dd262f,0x24c4a38b,0xa66d270e,0xa7fe2800,0x16480000,0xa73b2764,0x22d7a21f,
0xa7ea27f6,0x1cb29a46,0xa6dd270e,0x241da38b,0xa7c327d9,0x1fc69e3e,0xa66d26a7,0x24c4a472,0xa78827a8,0x2164a0a5,0xa5ed262f,0x255fa513,
0xa7c32800,0x1fc60000,0x24c4a21f,0x266da764,0xa5ed270e,0x255fa38b,0x273ba62f,0x22d7a513,0xa1642472,0x2788a6a7,0x27fea7d9,0x96489e3e,
0x1cb21a46,0x27eaa7f6,0x26dda7a8,0xa41d20a5,0xa73b2800,0x22d70000,0x255fa764,0xa5ed221f,0x9fc62513,0x27c3a62f,0x9cb2a0a5,0xa7ea27a8,
0x24c49e3e,0x266da7d9,0xa6dd2472,0xa41d26a7,0x27fea70e,0x1648a38b,0xa78827f6,0x21641a46,0xa66d2800,0x24c40000,0xa6dd221f,0xa41d2764,
0x216420a5,0x2788a7a8,0xa5ed27f6,0x255f9a46,0x27fea6a7,0x9648a472,0x22d71e3e,0x273ba7d9,0x1fc6a62f,0xa7c32513,0x27eaa70e,0x9cb2a38b,
0xa55f2800,0x25ed0000,0xa1642764,0x2788a21f,0x266d9a46,0x24c4a7f6,0x27c3a38b,0x1fc6a70e,0x241da7d9,0xa6dd1e3e,0x1cb2a6a7,0xa7ea2472,
0xa73b20a5,0xa2d727a8,0xa7fe2513,0x9648262f,0xa41d2800,0x26dd0000,0x27eaa21f,0x1cb2a764,0x27fea38b,0x1648a70e,0xa164a513,0xa788262f,
0xa2d7a472,0xa73b26a7,0xa55f27d9,0x25ed1e3e,0xa4c427f6,0x266d1a46,0x27c3a0a5,0x1fc6a7a8,0xa1642800,0x27880000,0x9648a764,0xa7fe221f,
0x26dda62f,0xa41da513,0xa4c427a8,0x266d20a5,0xa7ea1e3e,0x9cb227d9,0x27c3a472,0x9fc6a6a7,0x255f238b,0x25eda70e,0xa73b9a46,0xa2d727f6,
0x9cb22800,0x27ea0000,0xa7c3221f,0x1fc62764,0x22d7a7a8,0xa73ba0a5,0x27fe9a46,0x1648a7f6,0xa55f26a7,0x25ed2472,0xa7889e3e,0xa16427d9,
0x26dda513,0xa41da62f,0x266d238b,0x24c4a70e,0x16482800,0x27fe0000,0x22d72764,0x273ba21f,0x9cb2a7f6,0xa7ea1a46,0xa41da70e,0xa6dd238b,
0x1fc627d9,0x27c39e3e,0x24c426a7,0x266da472,0xa164a7a8,0xa78820a5,0xa55fa62f,0xa5ed2513,0x1fc62800,0x27c30000,0x266da21f,0xa4c4a764,
0xa55fa70e,0xa5ed238b,0xa2d7262f,0x273b2513,0x27882472,0x2164a6a7,0x9648a7d9,0xa7fe9e3e,0xa7ea9a46,0x1cb227f6,0x241d27a8,0x26dda0a5,
0x22d72800,0x273b0000,0xa5eda764,0xa55f221f,0xa7c3a513,0x9fc6262f,0x27ea20a5,0x9cb2a7a8,0x266d9e3e,0xa4c4a7d9,0xa41d2472,0x26dd26a7,
0x9648270e,0x27fe238b,0xa164a7f6,0xa7889a46,0x24c42800,0x266d0000,0xa41d221f,0x26dd2764,0xa788a0a5,0x216427a8,0xa55fa7f6,0xa5ed1a46,
0x9648a6a7,0xa7fea472,0x273b1e3e,0xa2d7a7d9,0x27c3262f,0x1fc6a513,0x1cb2270e,0x27ea238b,0x25ed2800,0x255f0000,0x27882764,0x2164a21f,
0xa4c41a46,0x266d27f6,0x9fc6238b,0x27c3270e,0xa6dda7d9,0xa41d1e3e,0xa7eaa6a7,0x9cb22472,0x22d7a0a5,0xa73ba7a8,0x1648a513,0xa7fea62f,
0x26dd2800,0x241d0000,0x1cb2a21f,0xa7eaa764,0x9648238b,0x27fe270e,0x27882513,0xa164a62f,0xa73ba472,0x22d726a7,0x25ed27d9,0x255f1e3e,
0xa66da7f6,0xa4c49a46,0x9fc620a5,0x27c327a8,0x27882800,0x21640000,0xa7fea764,0x1648221f,0x241d262f,0x26dd2513,0xa66da7a8,0xa4c4a0a5,
0x9cb21e3e,0x27ea27d9,0x9fc6a472,0xa7c3a6a7,0xa5eda38b,0x255f270e,0x22d71a46,0xa73ba7f6,0x27ea2800,0x1cb20000,0x1fc6221f,0x27c32764,
0x273b27a8,0x22d720a5,0x96481a46,0x27fe27f6,0x25ed26a7,0x255f2472,0xa1649e3e,0x278827d9,0x241d2513,0x26dd262f,0xa4c4a38b,0x266d270e,
0x255f25a8,0xa5eda5a8,0x2164221f,0xa788a764,0x24c42513,0xa66da62f,0x1fc620a5,0xa7c3a7a8,0x241d2472,0xa6dda6a7,0x1cb21e3e,0xa7eaa7d9,
0x22d7238b,0xa73ba70e,0x16481a46,0xa7fea7f6,0xa41da5a8,0x26dd25a8,0x27ea2764,0x1cb2221f,0x9648a0a5,0x27fe27a8,0x278827f6,0xa1649a46,
0x22d71e3e,0x273b27d9,0x255f26a7,0xa5eda472,0x266d2513,0x24c4262f,0x1fc6238b,0xa7c3a70e,0x216425a8,0xa788a5a8,0x1648a21f,0x27fe2764,
0xa41d9a46,0xa6dda7f6,0x266d238b,0x24c4270e,0xa7eaa6a7,0x9cb2a472,0x27c327d9,0x9fc61e3e,0xa5eda7a8,0x255f20a5,0x22d7262f,0xa73ba513,
0x9cb2a5a8,0x27ea25a8,0xa7c3a764,0x1fc6a21f,0x273b238b,0x22d7270e,0x9648a513,0x27fe262f,0x255f27d9,0xa5ed9e3e,0x27882472,0x216426a7,
0xa41d1a46,0xa6dda7f6,0x24c427a8,0xa66da0a5,0x964825a8,0xa7fea5a8,0xa2d7221f,0xa73ba764,0xa7eaa62f,0x1cb2a513,0xa6dda7a8,0x241da0a5,
0x1fc6a472,0x27c326a7,0x24c49e3e,0x266d27d9,0x2788270e,0xa164238b,0x25ed27f6,0xa55f1a46,0x1fc6a5a8,0x27c325a8,0x266d2764,0xa4c4221f,
0x25ed27a8,0xa55f20a5,0xa73b9a46,0xa2d7a7f6,0xa7889e3e,0xa164a7d9,0x1648a6a7,0x27fe2472,0x1cb2a62f,0x27ea2513,0x26dd270e,0xa41d238b,
0xa2d725a8,0xa73ba5a8,0x25eda21f,0x255f2764,0x9fc6a7f6,0x27c31a46,0x9cb2270e,0xa7eaa38b,0x266d26a7,0xa4c42472,0xa41da7d9,0x26dd9e3e,
0xa7fea0a5,0x9648a7a8,0x27882513,0xa164262f,0x24c4a5a8,0x266d25a8,0xa41da764,0x26dda21f,0xa164270e,0xa788a38b,0x25ed262f,0xa55f2513,
0x1648a7d9,0x27fe1e3e,0xa73ba472,0x22d7a6a7,0x1fc627f6,0xa7c31a46,0x27ea20a5,0x9cb227a8,0xa5ed25a8,0xa55fa5a8,0xa788221f,0xa164a764,
0x266da513,0x24c4262f,0x27c3a0a5,0x1fc627a8,0xa6dd2472,0xa41da6a7,0xa7ea1e3e,0x9cb2a7d9,0x273ba38b,0x22d7270e,0x27fe9a46,0x164827f6,
0x26dda5a8,0x241d25a8,0x1cb22764,0xa7ea221f,0xa7fe20a5,0x9648a7a8,0x2164a7f6,0x27881a46,0x273b1e3e,0xa2d727d9,0xa5ed26a7,0xa55fa472,
0xa4c4a513,0x266da62f,0x27c3a38b,0x1fc6270e,0xa78825a8,0xa164a5a8,0x27fea21f,0x96482764,0x26dd1a46,0xa41d27f6,0xa4c4a38b,0x266da70e,
0x9cb2a6a7,0x27eaa472,0x9fc627d9,0xa7c31e3e,0xa55f27a8,0xa5eda0a5,0x273ba62f,0x22d72513,0x27eaa5a8,0x1cb225a8,0x1fc6a764,0x27c3a21f,
0xa2d7a38b,0x273ba70e,0xa7fe2513,0x9648a62f,0xa5ed27d9,0xa55f9e3e,0x21642472,0xa78826a7,0x26dd9a46,0xa41d27f6,0x266da7a8,0x24c420a5,
0xa7fe25a8,0x1648a5a8,0xa73b221f,0x22d7a764,0x9cb2262f,0xa7ea2513,0xa41d27a8,0xa6dd20a5,0x27c3a472,0x9fc626a7,0x266d9e3e,0xa4c427d9,
0x2164a70e,0x2788a38b,0x255fa7f6,0x25ed9a46,0x27c3a5a8,0x9fc625a8,0xa4c42764,0xa66d221f,0x255fa7a8,0x25eda0a5,0x22d71a46,0xa73b27f6,
0xa1649e3e,0x2788a7d9,0x27fea6a7,0x96482472,0xa7ea262f,0x1cb2a513,0x241da70e,0x26dda38b,0xa73b25a8,0x22d7a5a8,0x255fa21f,0xa5ed2764,
0xa7c327f6,0x9fc69a46,0x27eaa70e,0x9cb2238b,0xa4c426a7,0xa66d2472,0x26dda7d9,0x241d9e3e,0x164820a5,0xa7fe27a8,0x2164a513,0x2788a62f,
0x266da5a8,0xa4c425a8,0x26dda764,0x241da21f,0x2788a70e,0xa164238b,0x255fa62f,0x25eda513,0x27fea7d9,0x96481e3e,0x22d7a472,0x273ba6a7,
0x27c3a7f6,0x1fc69a46,0x1cb2a0a5,0x27eaa7a8,0xa55f25a8,0x25eda5a8,0xa164221f,0x2788a764,0xa4c42513,0x266da62f,0x9fc620a5,0x27c3a7a8,
0xa41d2472,0x26dda6a7,0x9cb21e3e,0x27eaa7d9,0xa2d7238b,0x273ba70e,0x96481a46,0x27fea7f6,0x241da5a8,0xa6dd25a8,0xa7ea2764,0x9cb2221f,
0x1648a0a5,0xa7fe27a8,0xa78827f6,0x21649a46,0xa2d71e3e,0xa73b27d9,0xa55f26a7,0x25eda472,0xa66d2513,0xa4c4262f,0x9fc6238b,0x27c3a70e,
0xa16425a8,0x2788a5a8,0x9648a21f,0xa7fe2764,0x241d9a46,0x26dda7f6,0xa66d238b,0xa4c4270e,0x27eaa6a7,0x1cb2a472,0xa7c327d9,0x1fc61e3e,
0x25eda7a8,0xa55f20a5,0xa2d7262f,0x273ba513,0x1cb2a5a8,0xa7ea25a8,0x27c3a764,0x9fc6a21f,0xa73b238b,0xa2d7270e,0x1648a513,0xa7fe262f,
0xa55f27d9,0x25ed9e3e,0xa7882472,0xa16426a7,0x241d1a46,0x26dda7f6,0xa4c427a8,0x266da0a5,0x164825a8,0x27fea5a8,0x22d7221f,0x273ba764,
0x27eaa62f,0x9cb2a513,0x26dda7a8,0xa41da0a5,0x9fc6a472,0xa7c326a7,0xa4c49e3e,0xa66d27d9,0xa788270e,0x2164238b,0xa5ed27f6,0x255f1a46,
0x9fc6a5a8,0xa7c325a8,0xa66d2764,0x24c4221f,0xa5ed27a8,0x255f20a5,0x273b9a46,0x22d7a7f6,0x27889e3e,0x2164a7d9,0x9648a6a7,0xa7fe2472,
0x9cb2a62f,0xa7ea2513,0xa6dd270e,0x241d238b,0x22d725a8,0x273ba5a8,0xa5eda21f,0xa55f2764,0x1fc6a7f6,0xa7c31a46,0x1cb2270e,0x27eaa38b,
0xa66d26a7,0x24c42472,0x241da7d9,0xa6dd9e3e,0x27fea0a5,0x1648a7a8,0xa7882513,0x2164262f,0xa4c4a5a8,0xa66d25a8,0x241da764,0xa6dda21f,
0x2164270e,0x2788a38b,0xa5ed262f,0x255f2513,0x9648a7d9,0xa7fe1e3e,0x273ba472,0xa2d7a6a7,0x9fc627f6,0x27c31a46,0xa7ea20a5,0x1cb227a8,
0x25ed25a8,0x255fa5a8,0x2788221f,0x2164a764,0xa66da513,0xa4c4262f,0xa7c3a0a5,0x9fc627a8,0x26dd2472,0x241da6a7,0x27ea1e3e,0x1cb2a7d9,
0xa73ba38b,0xa2d7270e,0xa7fe9a46,0x964827f6,0xa6dda5a8,0xa41d25a8,0x9cb22764,0x27ea221f,0x27fe20a5,0x1648a7a8,0xa164a7f6,0xa7881a46,
0xa73b1e3e,0x22d727d9,0x25ed26a7,0x255fa472,0x24c4a513,0xa66da62f,0xa7c3a38b,0x9fc6270e,0x278825a8,0x2164a5a8,0xa7fea21f,0x16482764,
0xa6dd1a46,0x241d27f6,0x24c4a38b,0xa66da70e,0x1cb2a6a7,0xa7eaa472,0x1fc627d9,0x27c31e3e,0x255f27a8,0x25eda0a5,0xa73ba62f,0xa2d72513,
0xa7eaa5a8,0x9cb225a8,0x9fc6a764,0xa7c3a21f,0x22d7a38b,0xa73ba70e,0x27fe2513,0x1648a62f,0x25ed27d9,0x255f9e3e,0xa1642472,0x278826a7,
0xa6dd9a46,0x241d27f6,0xa66da7a8,0xa4c420a5,0x27fe25a8,0x9648a5a8,0x273b221f,0xa2d7a764,0x1cb2262f,0x27ea2513,0x241d27a8,0x26dd20a5,
0xa7c3a472,0x1fc626a7,0xa66d9e3e,0x24c427d9,0xa164a70e,0xa788a38b,0xa55fa7f6,0xa5ed9a46,0xa7c3a5a8,0x1fc625a8,0x24c42764,0x266d221f,
0xa55fa7a8,0xa5eda0a5,0xa2d71a46,0x273b27f6,0x21649e3e,0xa788a7d9,0xa7fea6a7,0x16482472,0x27ea262f,0x9cb2a513,0xa41da70e,0xa6dda38b,
0x273b25a8,0xa2d7a5a8,0xa55fa21f,0x25ed2764,0x27c327f6,0x1fc69a46,0xa7eaa70e,0x1cb2238b,0x24c426a7,0x266d2472,0xa6dda7d9,0xa41d9e3e,
0x964820a5,0x27fe27a8,0xa164a513,0xa788a62f,0xa66da5a8,0x24c425a8,0xa6dda764,0xa41da21f,0xa788a70e,0x2164238b,0xa55fa62f,0xa5eda513,
0xa7fea7d9,0x16481e3e,0xa2d7a472,0xa73ba6a7,0xa7c3a7f6,0x9fc69a46,0x9cb2a0a5,0xa7eaa7a8,
};

#define PROF(slot) do {} while (0)
#define PROF3(slot) do {} while (0)
#define PROF2(slot) do {} while (0)

__device__ __forceinline__ uint32_t smem_u32(const void* p) { return (uint32_t)__cvta_generic_to_shared(p); }

__device__ __forceinline__ void mbar_init(uint32_t a, uint32_t c) {
  asm volatile("mbarrier.init.shared::cta.b64 [%0], %1;\n" ::"r"(a), "r"(c) : "memory");
}
__device__ __forceinline__ void mbar_expect_tx(uint32_t a, uint32_t bytes) {
  asm volatile("mbarrier.arrive.expect_tx.shared::cta.b64 _, [%0], %1;\n" ::"r"(a), "r"(bytes) : "memory");
}
__device__ __forceinline__ void mbar_arrive_cluster(uint32_t cluster_addr) {
  asm volatile("mbarrier.arrive.shared::cluster.b64 _, [%0];\n" ::"r"(cluster_addr) : "memory");
}
__device__ __forceinline__ void mbar_arrive_cluster_n(uint32_t cluster_addr, uint32_t n) {
  asm volatile("mbarrier.arrive.shared::cluster.b64 _, [%0], %1;\n" ::"r"(cluster_addr), "r"(n) : "memory");
}
__device__ __forceinline__ bool mbar_try(uint32_t a, uint32_t parity) {
  uint32_t ok;
  asm volatile("{\n.reg .pred p;\nmbarrier.try_wait.parity.shared::cta.b64 p, [%1], %2;\nselp.u32 %0, 1, 0, p;\n}\n"
               : "=r"(ok) : "r"(a), "r"(parity) : "memory");
  return ok;
}
__device__ __forceinline__ void mbar_wait(uint32_t a, uint32_t parity) {
  if (mbar_try(a, parity)) return;
#pragma unroll 1
  for (int n = 0; n < SPIN_LIMIT; n++)
    if (mbar_try(a, parity)) break;
}
__device__ __forceinline__ void mbar_wait_idle(uint32_t a, uint32_t parity) {
#pragma unroll 1
  for (int n = 0; n < SPIN_LIMIT; n++) {
    uint32_t ok;
    asm volatile("{\n.reg .pred p;\nmbarrier.try_wait.parity.shared::cta.b64 p, [%1], %2, %3;\nselp.u32 %0, 1, 0, p;\n}\n"
                 : "=r"(ok) : "r"(a), "r"(parity), "r"(4000) : "memory");
    if (ok) break;
  }
}
__device__ __forceinline__ bool elect_one() {
  uint32_t p;
  asm volatile("{\n.reg .pred P;\nelect.sync _|P, 0xffffffff;\nselp.u32 %0, 1, 0, P;\n}\n" : "=r"(p));
  return p;
}
__device__ __forceinline__ uint32_t mapa(uint32_t a, uint32_t rank) {
  uint32_t r;
  asm volatile("mapa.shared::cluster.u32 %0, %1, %2;\n" : "=r"(r) : "r"(a), "r"(rank));
  return r;
}
__device__ __forceinline__ void nb_sync(int id, int n) { asm volatile("bar.sync %0, %1;\n" ::"r"(id), "r"(n) : "memory"); }
__device__ __forceinline__ void nb_arrive(int id, int n) { asm volatile("bar.arrive %0, %1;\n" ::"r"(id), "r"(n) : "memory"); }
__device__ __forceinline__ void cluster_sync_all() {
  asm volatile("barrier.cluster.arrive.relaxed.aligned;\nbarrier.cluster.wait.aligned;\n" ::: "memory");
}
__device__ __forceinline__ void fence_async_smem() { asm volatile("fence.proxy.async.shared::cta;\n" ::: "memory"); }
__device__ __forceinline__ void fence_async_all() { asm volatile("fence.proxy.async.global;\n" ::: "memory"); }

__device__ __forceinline__ void tma_load_3d(uint32_t dst, const CUtensorMap* tm, uint32_t bar, int c0, int c1, int c2) {
  asm volatile(
      "cp.async.bulk.tensor.3d.shared::cluster.global.mbarrier::complete_tx::bytes [%0], [%1, {%3, %4, %5}], [%2];\n"
      ::"r"(dst), "l"(tm), "r"(bar), "r"(c0), "r"(c1), "r"(c2) : "memory");
}
__device__ __forceinline__ void tma_load_4d(uint32_t dst, const CUtensorMap* tm, uint32_t bar, int c0, int c1, int c2, int c3) {
  asm volatile(
      "cp.async.bulk.tensor.4d.shared::cluster.global.mbarrier::complete_tx::bytes [%0], [%1, {%3, %4, %5, %6}], [%2];\n"
      ::"r"(dst), "l"(tm), "r"(bar), "r"(c0), "r"(c1), "r"(c2), "r"(c3) : "memory");
}
__device__ __forceinline__ void tma_load_3d_mc(uint32_t dst, const CUtensorMap* tm, uint32_t bar, int c0, int c1, int c2) {
  asm volatile(
      "cp.async.bulk.tensor.3d.shared::cluster.global.mbarrier::complete_tx::bytes.multicast::cluster [%0], [%1, {%3, %4, %5}], [%2], %6;\n"
      ::"r"(dst), "l"(tm), "r"(bar), "r"(c0), "r"(c1), "r"(c2), "h"((uint16_t)3) : "memory");
}
__device__ __forceinline__ void tma_load_5d(uint32_t dst, const CUtensorMap* tm, uint32_t bar, int c0, int c4) {
  asm volatile(
      "cp.async.bulk.tensor.5d.shared::cluster.global.mbarrier::complete_tx::bytes [%0], [%1, {%3, %5, %5, %5, %4}], [%2];\n"
      ::"r"(dst), "l"(tm), "r"(bar), "r"(c0), "r"(c4), "r"(0) : "memory");
}
__device__ __forceinline__ void bulk_load(uint32_t dst, const void* src, uint32_t bytes, uint32_t bar) {
  asm volatile("cp.async.bulk.shared::cluster.global.mbarrier::complete_tx::bytes [%0], [%1], %2, [%3];\n"
               ::"r"(dst), "l"(src), "r"(bytes), "r"(bar) : "memory");
}
__device__ __forceinline__ void bulk_commit() { asm volatile("cp.async.bulk.commit_group;\n" ::: "memory"); }
__device__ __forceinline__ void bulk_wait0() { asm volatile("cp.async.bulk.wait_group 0;\n" ::: "memory"); }
__device__ __forceinline__ void prefetch_tmap(const CUtensorMap* tm) {
  asm volatile("prefetch.tensormap [%0];\n" ::"l"(tm) : "memory");
}

__device__ __forceinline__ void wg_fence() { asm volatile("wgmma.fence.sync.aligned;\n" ::: "memory"); }
__device__ __forceinline__ void wg_commit() { asm volatile("wgmma.commit_group.sync.aligned;\n" ::: "memory"); }
template <int N> __device__ __forceinline__ void wg_wait() {
  asm volatile("wgmma.wait_group.sync.aligned %0;\n" ::"n"(N) : "memory");
}
__device__ __forceinline__ uint64_t mkdesc(uint32_t addr, uint32_t lbo, uint32_t sbo, uint32_t swz) {
  return (uint64_t)((addr & 0x3FFFF) >> 4) | ((uint64_t)(lbo >> 4) << 16) | ((uint64_t)(sbo >> 4) << 32) |
         ((uint64_t)swz << 62);
}

#define R4(d, o) "+f"(d[o + 0]), "+f"(d[o + 1]), "+f"(d[o + 2]), "+f"(d[o + 3])
#define R8(d, o) R4(d, o), R4(d, o + 4)
#define R16(d, o) R8(d, o), R8(d, o + 8)
#define R32(d, o) R16(d, o), R16(d, o + 16)
#define R64(d, o) R32(d, o), R32(d, o + 32)

__device__ __forceinline__ void wgmma_n192(float (&d)[96], uint64_t da, uint64_t db, uint32_t acc) {
  asm volatile(
      "{\n.reg .pred p;\nsetp.ne.u32 p, %98, 0;\n"
      "wgmma.mma_async.sync.aligned.m64n192k16.f32.bf16.bf16 "
      "{%0,%1,%2,%3,%4,%5,%6,%7,%8,%9,%10,%11,%12,%13,%14,%15,%16,%17,%18,%19,%20,%21,%22,%23,%24,%25,%26,%27,%28,%29,%30,%31,"
      "%32,%33,%34,%35,%36,%37,%38,%39,%40,%41,%42,%43,%44,%45,%46,%47,%48,%49,%50,%51,%52,%53,%54,%55,%56,%57,%58,%59,%60,%61,%62,%63,"
      "%64,%65,%66,%67,%68,%69,%70,%71,%72,%73,%74,%75,%76,%77,%78,%79,%80,%81,%82,%83,%84,%85,%86,%87,%88,%89,%90,%91,%92,%93,%94,%95}, "
      "%96, %97, p, 1, 1, 0, 1;\n}\n"
      : R64(d, 0), R32(d, 64)
      : "l"(da), "l"(db), "r"(acc));
}
__device__ __forceinline__ void wgmma_n128(float (&d)[64], uint64_t da, uint64_t db, uint32_t acc) {
  asm volatile(
      "{\n.reg .pred p;\nsetp.ne.u32 p, %66, 0;\n"
      "wgmma.mma_async.sync.aligned.m64n128k16.f32.bf16.bf16 "
      "{%0,%1,%2,%3,%4,%5,%6,%7,%8,%9,%10,%11,%12,%13,%14,%15,%16,%17,%18,%19,%20,%21,%22,%23,%24,%25,%26,%27,%28,%29,%30,%31,"
      "%32,%33,%34,%35,%36,%37,%38,%39,%40,%41,%42,%43,%44,%45,%46,%47,%48,%49,%50,%51,%52,%53,%54,%55,%56,%57,%58,%59,%60,%61,%62,%63}, "
      "%64, %65, p, 1, 1, 0, 1;\n}\n"
      : R64(d, 0)
      : "l"(da), "l"(db), "r"(acc));
}
template <int N> __device__ __forceinline__ void fence_regs(float (&d)[N]) {
#pragma unroll
  for (int i = 0; i < N; i++) asm volatile("" : "+f"(d[i])::"memory");
}

__device__ __forceinline__ void mma16816(float (&d)[4], uint32_t a0, uint32_t a1, uint32_t a2, uint32_t a3, uint32_t b0,
                                         uint32_t b1) {
  asm("mma.sync.aligned.m16n8k16.row.col.f32.bf16.bf16.f32 {%0,%1,%2,%3}, {%4,%5,%6,%7}, {%8,%9}, {%0,%1,%2,%3};\n"
      : "+f"(d[0]), "+f"(d[1]), "+f"(d[2]), "+f"(d[3])
      : "r"(a0), "r"(a1), "r"(a2), "r"(a3), "r"(b0), "r"(b1));
}
__device__ __forceinline__ void mma16816_z(float (&d)[4], uint32_t a0, uint32_t a1, uint32_t a2, uint32_t a3, uint32_t b0,
                                           uint32_t b1) {
  asm("mma.sync.aligned.m16n8k16.row.col.f32.bf16.bf16.f32 {%0,%1,%2,%3}, {%4,%5,%6,%7}, {%8,%9}, {%10,%10,%10,%10};\n"
      : "=f"(d[0]), "=f"(d[1]), "=f"(d[2]), "=f"(d[3])
      : "r"(a0), "r"(a1), "r"(a2), "r"(a3), "r"(b0), "r"(b1), "f"(0.f));
}
__device__ __forceinline__ void ldsm4t(uint32_t (&r)[4], uint32_t a) {
  asm volatile("ldmatrix.sync.aligned.m8n8.x4.trans.shared.b16 {%0,%1,%2,%3}, [%4];\n"
               : "=r"(r[0]), "=r"(r[1]), "=r"(r[2]), "=r"(r[3]) : "r"(a) : "memory");
}
__device__ __forceinline__ void ldsm2t(uint32_t& r0, uint32_t& r1, uint32_t a) {
  asm volatile("ldmatrix.sync.aligned.m8n8.x2.trans.shared.b16 {%0,%1}, [%2];\n" : "=r"(r0), "=r"(r1) : "r"(a) : "memory");
}
__device__ __forceinline__ void st_async128(uint32_t a, uint32_t bar, uint32_t x, uint32_t y, uint32_t z, uint32_t w) {
  asm volatile("st.async.weak.shared::cluster.mbarrier::complete_tx::bytes.v4.b32 [%0], {%2,%3,%4,%5}, [%1];\n"
               ::"r"(a), "r"(bar), "r"(x), "r"(y), "r"(z), "r"(w) : "memory");
}
__device__ __forceinline__ void mbar_arrive(uint32_t a) {
  asm volatile("mbarrier.arrive.shared::cta.b64 _, [%0];\n" ::"r"(a) : "memory");
}
__device__ __forceinline__ void stsm4(uint32_t a, uint32_t r0, uint32_t r1, uint32_t r2, uint32_t r3) {
  asm volatile("stmatrix.sync.aligned.m8n8.x4.shared.b16 [%0], {%1,%2,%3,%4};\n"
               ::"r"(a), "r"(r0), "r"(r1), "r"(r2), "r"(r3) : "memory");
}
__device__ __forceinline__ void stsm4t(uint32_t a, uint32_t r0, uint32_t r1, uint32_t r2, uint32_t r3) {
  asm volatile("stmatrix.sync.aligned.m8n8.x4.trans.shared.b16 [%0], {%1,%2,%3,%4};\n"
               ::"r"(a), "r"(r0), "r"(r1), "r"(r2), "r"(r3) : "memory");
}
__device__ __forceinline__ uint2 lds64(uint32_t a) {
  uint2 v;
  asm volatile("ld.shared.v2.u32 {%0,%1}, [%2];\n" : "=r"(v.x), "=r"(v.y) : "r"(a));
  return v;
}
__device__ __forceinline__ uint4 lds128(uint32_t a) {
  uint4 v;
  asm volatile("ld.shared.v4.u32 {%0,%1,%2,%3}, [%4];\n" : "=r"(v.x), "=r"(v.y), "=r"(v.z), "=r"(v.w) : "r"(a) : "memory");
  return v;
}
__device__ __forceinline__ void sts128(uint32_t a, uint32_t x, uint32_t y, uint32_t z, uint32_t w) {
  asm volatile("st.shared.v4.u32 [%0], {%1,%2,%3,%4};\n" ::"r"(a), "r"(x), "r"(y), "r"(z), "r"(w) : "memory");
}
__device__ __forceinline__ uint32_t pack_bf16(float lo, float hi) {
  uint32_t r;
  asm("cvt.rn.bf16x2.f32 %0, %1, %2;\n" : "=r"(r) : "f"(hi), "f"(lo));
  return r;
}
__device__ __forceinline__ uint32_t bmul2(uint32_t a, uint32_t b) {
  uint32_t r;
  asm("mul.rn.bf16x2 %0, %1, %2;\n" : "=r"(r) : "r"(a), "r"(b));
  return r;
}
__device__ __forceinline__ uint32_t bmax2(uint32_t a, uint32_t b) {
  uint32_t r;
  asm("max.bf16x2 %0, %1, %2;\n" : "=r"(r) : "r"(a), "r"(b));
  return r;
}
__device__ __forceinline__ uint32_t bfma2(uint32_t a, uint32_t b, uint32_t c) {
  uint32_t r;
  asm("fma.rn.bf16x2 %0, %1, %2, %3;\n" : "=r"(r) : "r"(a), "r"(b), "r"(c));
  return r;
}
__device__ __forceinline__ uint32_t badd2(uint32_t a, uint32_t b) {
  uint32_t r;
  asm("add.rn.bf16x2 %0, %1, %2;\n" : "=r"(r) : "r"(a), "r"(b));
  return r;
}
__device__ __forceinline__ void prefetch_l2(const void* p) { asm volatile("prefetch.global.L2 [%0];\n" ::"l"(p)); }
__device__ __forceinline__ void cp_async16n(uint32_t dst, const void* src) {
  asm volatile("cp.async.cg.shared.global [%0], [%1], 16;\n" ::"r"(dst), "l"(src) : "memory");
}
__device__ __forceinline__ void cp_async16(uint32_t dst, const void* src, uint32_t srcbytes) {
  asm volatile("cp.async.cg.shared.global.L2::256B [%0], [%1], 16, %2;\n" ::"r"(dst), "l"(src), "r"(srcbytes) : "memory");
}
__device__ __forceinline__ uint32_t ld_acquire(const uint32_t* p) {
  uint32_t v;
  asm volatile("ld.acquire.gpu.global.u32 %0, [%1];\n" : "=r"(v) : "l"(p) : "memory");
  return v;
}
__device__ __forceinline__ uint32_t ld_relaxed(const uint32_t* p) {
  uint32_t v;
  asm volatile("ld.relaxed.gpu.global.u32 %0, [%1];\n" : "=r"(v) : "l"(p) : "memory");
  return v;
}
__device__ __forceinline__ void st_release(uint32_t* p, uint32_t v) {
  asm volatile("st.release.gpu.global.u32 [%0], %1;\n" ::"l"(p), "r"(v) : "memory");
}
__device__ __forceinline__ void wait_flag(const uint32_t* p, uint32_t want) {
  int n = 0;
  while (ld_relaxed(p) != want && ++n < SPIN_LIMIT) __nanosleep(40);
  (void)ld_acquire(p);
}

struct Params {
  const __nv_bfloat16* x;
  const __nv_bfloat16* w;
  const __nv_bfloat16* q;
  const __nv_bfloat16* k;
  const __nv_bfloat16* v;
  const __nv_bfloat16* shift_k;
  const __nv_bfloat16* ssm_k;
  const __nv_bfloat16* ssm_D;
  const __nv_bfloat16* wo;
  __nv_bfloat16* out;
};

__device__ __forceinline__ uint32_t lds32(uint32_t a) {
  uint32_t v;
  asm volatile("ld.shared.u32 %0, [%1];\n" : "=r"(v) : "r"(a));
  return v;
}
#define W4(d, o) "=f"(d[o + 0]), "=f"(d[o + 1]), "=f"(d[o + 2]), "=f"(d[o + 3])
#define W8(d, o) W4(d, o), W4(d, o + 4)
#define W16(d, o) W8(d, o), W8(d, o + 8)
#define U4(c, d, o) c(d[o + 0]), c(d[o + 1]), c(d[o + 2]), c(d[o + 3])
#define U8(c, d, o) U4(c, d, o), U4(c, d, o + 4)
#define U16(c, d, o) U8(c, d, o), U8(c, d, o + 8)
#define U32(c, d, o) U16(c, d, o), U16(c, d, o + 16)
#define D32 "{%0,%1,%2,%3,%4,%5,%6,%7,%8,%9,%10,%11,%12,%13,%14,%15,%16,%17,%18,%19,%20,%21,%22,%23,%24,%25,%26,%27,%28,%29,%30,%31}"
#define D16 "{%0,%1,%2,%3,%4,%5,%6,%7,%8,%9,%10,%11,%12,%13,%14,%15}"
#define D8 "{%0,%1,%2,%3,%4,%5,%6,%7}"
template <int ACC> __device__ __forceinline__ void hmma_n128t(uint32_t (&d)[32], const uint32_t (&a)[4], uint64_t db) {
  if (ACC)
    asm volatile("wgmma.mma_async.sync.aligned.m64n128k16.f16.f16.f16 " D32 ", {%32,%33,%34,%35}, %36, 1, 1, 1, 1;\n"
                 : U32("+r", d, 0) : "r"(a[0]), "r"(a[1]), "r"(a[2]), "r"(a[3]), "l"(db));
  else
    asm volatile("wgmma.mma_async.sync.aligned.m64n128k16.f16.f16.f16 " D32 ", {%32,%33,%34,%35}, %36, 0, 1, 1, 1;\n"
                 : U32("=r", d, 0) : "r"(a[0]), "r"(a[1]), "r"(a[2]), "r"(a[3]), "l"(db));
}
template <int ACC, int TB> __device__ __forceinline__ void hmma_n32(uint32_t (&d)[8], const uint32_t (&a)[4], uint64_t db) {
  if (ACC)
    asm volatile("wgmma.mma_async.sync.aligned.m64n32k16.f16.f16.f16 " D8 ", {%8,%9,%10,%11}, %12, 1, 1, 1, %13;\n"
                 : U8("+r", d, 0) : "r"(a[0]), "r"(a[1]), "r"(a[2]), "r"(a[3]), "l"(db), "n"(TB));
  else
    asm volatile("wgmma.mma_async.sync.aligned.m64n32k16.f16.f16.f16 " D8 ", {%8,%9,%10,%11}, %12, 0, 1, 1, %13;\n"
                 : U8("=r", d, 0) : "r"(a[0]), "r"(a[1]), "r"(a[2]), "r"(a[3]), "l"(db), "n"(TB));
}
template <int ACC> __device__ __forceinline__ void hmma_n64t(uint32_t (&d)[16], const uint32_t (&a)[4], uint64_t db) {
  if (ACC)
    asm volatile("wgmma.mma_async.sync.aligned.m64n64k16.f16.f16.f16 " D16 ", {%16,%17,%18,%19}, %20, 1, 1, 1, 1;\n"
                 : U16("+r", d, 0) : "r"(a[0]), "r"(a[1]), "r"(a[2]), "r"(a[3]), "l"(db));
  else
    asm volatile("wgmma.mma_async.sync.aligned.m64n64k16.f16.f16.f16 " D16 ", {%16,%17,%18,%19}, %20, 0, 1, 1, 1;\n"
                 : U16("=r", d, 0) : "r"(a[0]), "r"(a[1]), "r"(a[2]), "r"(a[3]), "l"(db));
}
template <int N> __device__ __forceinline__ void fence_regs(uint32_t (&d)[N]) {
#pragma unroll
  for (int i = 0; i < N; i++) asm volatile("" : "+r"(d[i])::"memory");
}
__device__ __forceinline__ uint32_t hmul(uint32_t a, uint32_t b) { uint32_t r; asm("mul.rn.f16x2 %0, %1, %2;\n" : "=r"(r) : "r"(a), "r"(b)); return r; }
__device__ __forceinline__ uint32_t hadd(uint32_t a, uint32_t b) { uint32_t r; asm("add.rn.f16x2 %0, %1, %2;\n" : "=r"(r) : "r"(a), "r"(b)); return r; }
__device__ __forceinline__ uint32_t hsub(uint32_t a, uint32_t b) { uint32_t r; asm("sub.rn.f16x2 %0, %1, %2;\n" : "=r"(r) : "r"(a), "r"(b)); return r; }
__device__ __forceinline__ uint32_t hfma(uint32_t a, uint32_t b, uint32_t c) { uint32_t r; asm("fma.rn.f16x2 %0, %1, %2, %3;\n" : "=r"(r) : "r"(a), "r"(b), "r"(c)); return r; }
__device__ __forceinline__ uint32_t hfnma(uint32_t a, uint32_t b, uint32_t c) {
  uint32_t r;
  asm("{\n.reg .b32 t;\nneg.f16x2 t, %1;\nfma.rn.f16x2 %0, t, %2, %3;\n}\n" : "=r"(r) : "r"(a), "r"(b), "r"(c));
  return r;
}
__device__ __forceinline__ uint32_t hrefl(uint32_t p, uint32_t s) {
  uint32_t r;
  asm("{\n.reg .b32 t;\nneg.f16x2 t, %2;\nfma.rn.f16x2 %0, %1, %3, t;\n}\n" : "=r"(r) : "r"(p), "r"(s), "r"(0x40004000u));
  return r;
}
__device__ __forceinline__ void bfly(uint32_t xr, uint32_t xi, uint32_t tr, uint32_t ti, uint32_t yr, uint32_t yi, uint32_t ur,
                                     uint32_t ui, uint32_t& sr, uint32_t& si, uint32_t& dr, uint32_t& di) {
  const uint32_t pr = hfnma(xi, ti, hmul(xr, tr)), pi = hfma(xi, tr, hmul(xr, ti));
  sr = hfnma(yi, ui, hfma(yr, ur, pr));
  si = hfma(yi, ur, hfma(yr, ui, pi));
  dr = hrefl(pr, sr);
  di = hrefl(pi, si);
}
template <int BH> __device__ __forceinline__ void fft_e1(const uint32_t (&d)[32], const uint32_t (&tw)[16], uint32_t (&a2)[2][2][4]) {
#pragma unroll
  for (int be = 0; be < 2; be++)
#pragma unroll
    for (int s = 0; s < 2; s++) {
      const int o = 16 * s + 8 * be + 2 * BH, p = 2 * BH;
      bfly(d[o], d[o + 1], tw[p], tw[p + 1], d[o + 4], d[o + 5], tw[p + 4], tw[p + 5], a2[be][0][s], a2[be][0][2 + s],
           a2[be][1][s], a2[be][1][2 + s]);
    }
}
__device__ __forceinline__ uint32_t hfms(uint32_t a, uint32_t b, uint32_t c) {
  uint32_t r;
  asm("{\n.reg .b32 t;\nneg.f16x2 t, %3;\nfma.rn.f16x2 %0, %1, %2, t;\n}\n" : "=r"(r) : "r"(a), "r"(b), "r"(c));
  return r;
}
template <int C, int J> __device__ __forceinline__ void fft_e2(const uint32_t (&d0)[8], const uint32_t (&d1)[8], uint32_t (&a3)[2][4]) {
  const uint32_t ur = d0[2 * J], ui = d0[4 + 2 * J], hr = d0[2 * J + 1], hi = d0[5 + 2 * J];
  const uint32_t vr = d1[2 * J], vi = d1[4 + 2 * J], gr = d1[2 * J + 1], gi = d1[5 + 2 * J];
  const uint32_t pr = hfnma(ui, hi, hmul(ur, hr)), pi = hfma(ui, hr, hmul(ur, hi));
  a3[0][2 + C] = pr;
  a3[0][C] = pi;
  a3[1][2 + C] = hfnma(vi, hi, hfma(vr, hr, hfnma(ui, gi, hfms(ur, gr, pi))));
  a3[1][C] = hfma(vi, hr, hfma(vr, hi, hfma(ui, gr, hfma(ur, gi, pr))));
}
__device__ __forceinline__ void fft_e3(const uint32_t (&d)[2][8], const uint32_t (&tw)[16], uint32_t zaddr) {
#pragma unroll
  for (int rho = 0; rho < 2; rho++) {
    uint32_t zr[4], zi[4];
#pragma unroll
    for (int nb = 0; nb < 4; nb++) {
      const uint32_t xi = d[nb >> 1][2 * (nb & 1) + rho], xr = d[nb >> 1][4 + 2 * (nb & 1) + rho];
      const uint32_t tr = tw[8 + 4 * rho + 2 * (nb & 1)], ti = tw[9 + 4 * rho + 2 * (nb & 1)];
      zr[nb] = hfnma(xi, ti, hmul(xr, tr));
      zi[nb] = hfma(xi, tr, hmul(xr, ti));
    }
    stsm4(zaddr + rho * 2048, zr[0], zr[1], zr[2], zr[3]);
    stsm4(zaddr + rho * 2048 + 1024, zi[0], zi[1], zi[2], zi[3]);
  }
}
__device__ __forceinline__ float bf_lo(uint32_t v) {
  uint32_t r;
  asm("prmt.b32 %0, %1, 0, 0x1044;\n" : "=r"(r) : "r"(v));
  return __uint_as_float(r);
}
__device__ __forceinline__ float bf_hi(uint32_t v) { return __uint_as_float(v & 0xffff0000u); }
__device__ __forceinline__ float ex2(float x) {
  float r;
  asm("ex2.approx.ftz.f32 %0, %1;\n" : "=f"(r) : "f"(x));
  return r;
}
__device__ __forceinline__ float rcp(float x) {
  float r;
  asm("rcp.approx.ftz.f32 %0, %1;\n" : "=f"(r) : "f"(x));
  return r;
}

__device__ __forceinline__ int g2_a(int s) { return ((0xA1054 >> (4 * s)) & 15) * 16384; }
__device__ __forceinline__ int g2_b(int s) { return ((0xCDB32 >> (4 * s)) & 15) * 16384; }
static_assert(OFF_U == 10 * 16384 && OFF_H == 12 * 16384 && OFF_OP == 4 * 16384, "units");
__device__ __forceinline__ int g2_k(int hp, int i) {
  return i < 2 ? hp ^ 1 ^ i : i < 4 ? (hp & ~1) ^ i : ((hp & ~3) + i) & 15; }
__device__ __forceinline__ int y_slot(int wg, int it) {
  static_assert(T_B2 == T_TW + 8192 && T_A1 == T_B2 + 4096, "y slots");
  return OFF_T + T_TW + ((it + 3) & 3) * 4096 + wg * 2048;
}

__device__ __forceinline__ void to_arr(uint32_t (&d)[4], uint4 v) { d[0] = v.x; d[1] = v.y; d[2] = v.z; d[3] = v.w; }

__device__ __forceinline__ void attn_stage(uint32_t sb, int blk, int lane, const float (&acc)[96], uint32_t (&k1)[2][4]) {
  const int lr = lane & 7, lm = lane >> 3;
  const uint32_t base = sb + OFF_VP + (blk * 16 + lr + 8 * (lm & 1)) * 128;
#pragma unroll
  for (int i = 0; i < 8; i++) k1[i >> 2][i & 3] = pack_bf16(acc[34 + 4 * i], acc[35 + 4 * i]);
  const uint32_t kh = sb + OFF_KH + blk * 2048 + lane * 16;
  sts128(kh, k1[0][0], k1[0][1], k1[0][2], k1[0][3]);
  sts128(kh + 512, k1[1][0], k1[1][1], k1[1][2], k1[1][3]);
#pragma unroll
  for (int j = 0; j < 8; j += 2)
    stsm4(base + (((j + (lm >> 1)) ^ lr) << 4), pack_bf16(acc[64 + 4 * j], acc[65 + 4 * j]),
          pack_bf16(acc[66 + 4 * j], acc[67 + 4 * j]), pack_bf16(acc[68 + 4 * j], acc[69 + 4 * j]),
          pack_bf16(acc[70 + 4 * j], acc[71 + 4 * j]));
}
__device__ __forceinline__ void attn_pack(const float (&acc)[96], uint32_t (&qa)[2][8], uint32_t (&k0)[2][4]) {
#pragma unroll
  for (int hd = 0; hd < 2; hd++) {
#pragma unroll
    for (int i = 0; i < 8; i++) {
      asm volatile("cvt.rn.bf16x2.f32 %0, %1, %2;\n" : "=r"(qa[hd][i]) : "f"(acc[16 * hd + 2 * i + 1]), "f"(acc[16 * hd + 2 * i]));
    }
#pragma unroll
    for (int i = 0; i < 4; i++) {
      asm volatile("cvt.rn.bf16x2.f32 %0, %1, %2;\n" : "=r"(k0[hd][i]) : "f"(acc[33 + 16 * hd + 4 * i]), "f"(acc[32 + 16 * hd + 4 * i]));
    }
  }
}
__device__ __forceinline__ void attn_own(const uint32_t (&k0)[2][4], const uint32_t (&k1)[2][4], bool le0, bool le1,
                                         const uint32_t (&qa)[2][8], float (&l)[2][4]) {
#pragma unroll
  for (int hd = 0; hd < 2; hd++) {
    float s0[4], s1[4];
    mma16816_z(s0, qa[hd][0], qa[hd][1], qa[hd][2], qa[hd][3], k0[hd][0], k0[hd][1]);
    mma16816_z(s1, qa[hd][0], qa[hd][1], qa[hd][2], qa[hd][3], k1[hd][0], k1[hd][1]);
    mma16816(s0, qa[hd][4], qa[hd][5], qa[hd][6], qa[hd][7], k0[hd][2], k0[hd][3]);
    mma16816(s1, qa[hd][4], qa[hd][5], qa[hd][6], qa[hd][7], k1[hd][2], k1[hd][3]);
    l[hd][0] = s0[0];
    l[hd][1] = s0[1];
    l[hd][2] = le0 ? s1[2] : s0[2];
    l[hd][3] = le1 ? s1[3] : s0[3];
  }
}
template <int N> __device__ __forceinline__ void quad_softmax(float (&x)[N][2], uint32_t (&pp)[N]) {
  const float c2 = 1.4426950408889634f;
  uint32_t q[N], mx[N / 2];
#pragma unroll
  for (int n = 0; n < N; n++) {
    const uint32_t r = pack_bf16(x[n][0], x[n][1]);
    q[n] = bfma2(r, 0x3e353e35u, bmul2(r, 0x379e379eu));
    x[n][0] = bf_lo(q[n]);
    x[n][1] = bf_hi(q[n]);
  }
#pragma unroll
  for (int n = 0; n < N / 2; n++)
    mx[n] = bmax2(__byte_perm(q[2 * n], q[2 * n + 1], 0x5410), __byte_perm(q[2 * n], q[2 * n + 1], 0x7632));
#pragma unroll
  for (int o = 1; o <= 2; o++)
#pragma unroll
    for (int n = 0; n < N / 2; n++) mx[n] = bmax2(mx[n], __shfl_xor_sync(0xffffffffu, mx[n], o));
  float m[N], t[N];
#pragma unroll
  for (int n = 0; n < N / 2; n++) {
    m[2 * n] = bf_lo(mx[n]);
    m[2 * n + 1] = bf_hi(mx[n]);
  }
#pragma unroll
  for (int n = 0; n < N; n++) {
    const float nm = -m[n] * c2;
    x[n][0] = ex2(fmaf(x[n][0], c2, nm));
    x[n][1] = ex2(fmaf(x[n][1], c2, nm));
    t[n] = x[n][0] + x[n][1];
  }
#pragma unroll
  for (int o = 1; o <= 2; o++)
#pragma unroll
    for (int n = 0; n < N; n++) t[n] += __shfl_xor_sync(0xffffffffu, t[n], o);
#pragma unroll
  for (int n = 0; n < N; n++) {
    const float inv = rcp(t[n]);
    pp[n] = pack_bf16(x[n][0] * inv, x[n][1] * inv);
  }
}
__device__ __forceinline__ void attn_pv(uint32_t dst, const uint32_t (&va)[4], const uint32_t (&vb)[4], uint32_t pp,
                                        uint32_t maskLE) {
  const uint32_t b0 = pp & ~maskLE, b1 = pp & maskLE;
  float oa[4], ob[4];
  mma16816_z(oa, va[0], va[1], va[2], va[3], b0, b1);
  mma16816_z(ob, vb[0], vb[1], vb[2], vb[3], b0, b1);
  stsm4t(dst, pack_bf16(oa[0], oa[1]), pack_bf16(oa[2], oa[3]), pack_bf16(ob[0], ob[1]), pack_bf16(ob[2], ob[3]));
}

template <int MODE>
__global__ void __cluster_dims__(2, 1, 1) __launch_bounds__(NTHREADS, 1)
fused_kernel(const Params p, const __grid_constant__ CUtensorMap tmX, const __grid_constant__ CUtensorMap tmW,
             const __grid_constant__ CUtensorMap tmWo,
             const __grid_constant__ CUtensorMap tmQ,
             const __grid_constant__ CUtensorMap tmXh, const __grid_constant__ CUtensorMap tmWh) {
  extern __shared__ __align__(1024) uint8_t smem[];
  const uint32_t sb = smem_u32(smem) - OFF_L0;
  const uint32_t bars = sb + OFF_BAR;
  const int tid = threadIdx.x, lane = tid & 31, warp = __shfl_sync(0xffffffffu, tid >> 5, 0);
  const int rank = blockIdx.x & 1;
  const bool halo_cta = blockIdx.x < 4;
  if (halo_cta && MODE != 0) return;
  int grp, mem;
  {
    const int t = (blockIdx.x >> 1) - 4, u = t - 32;
    const int q7 = (u * 37) >> 8;
    const bool lo = (unsigned)t < 32u, mid = (unsigned)u < 28u;
    grp = lo ? (t & 7) : (mid ? 1 + u - 7 * q7 : 0);
    mem = lo ? (t >> 3) : (mid ? 4 + q7 : (t < 0 ? t + 6 : t - 54));
  }
  const int rg = (grp >> 2) * 4 + (mem >> 1), hp = (grp & 3) * 4 + (mem & 1) * 2 + rank;
  const int rb2 = (grp >> 2) * 8 + mem, cb2 = (grp & 3) * 2 + rank;
  const int chb = grp * 16 + mem * 2 + rank;
  const int cta = rg * 16 + hp;
  const int par = rg >> 2, gidx = rg & 3;

  if (tid < 256 && !halo_cta && MODE != 2) {
    const int r = tid >> 3, c = tid & 7;
    const uint32_t so = r * 128 + ((c ^ (r & 7)) << 4);
    const __nv_bfloat16* wg0 = p.w + (size_t)r * (3 * DM) + hp * 64 + c * 8;
    const __nv_bfloat16* xg0 = p.x + (size_t)(2 * (gidx * 256 + r) + par) * DM + c * 8;
#pragma unroll
    for (int j = 0; j < 3; j++) cp_async16n(sb + OFF_1B + j * 4096 + so, wg0 + j * DM);
#pragma unroll
    for (int i = 0; i < 8; i++) cp_async16n(sb + i * 4096 + so, xg0 + (size_t)i * 64 * DM);
    asm volatile("cp.async.commit_group;\n" ::: "memory");
  }
  if (tid == 256) {
    prefetch_tmap(halo_cta ? &tmXh : &tmX);
#pragma unroll
    for (int i = 0; i < NS1B; i++) mbar_init(bars + 8 * (BAR_FULLB + i), 1);
#pragma unroll
    for (int i = 0; i < NS1A; i++) mbar_init(bars + 8 * (BAR_FULLA + i), 1);
    asm volatile("fence.mbarrier_init.release.cluster;\n" ::: "memory");
    if (!halo_cta && MODE != 2) {
      mbar_expect_tx(bars + 8 * (BAR_FULLB + 1), STG1B);
      tma_load_3d(sb + OFF_1B + 1 * STG1B, &tmW, bars + 8 * (BAR_FULLB + 1), hp * 64, 32, 0);
      mbar_expect_tx(bars + 8 * (BAR_FULLB + 2), STG1B);
      tma_load_3d(sb + OFF_1B + 2 * STG1B, &tmW, bars + 8 * (BAR_FULLB + 2), hp * 64, 64, 0);
    } else {
      prefetch_tmap(&tmWh);
    }
  } else if (tid == 288) {
#pragma unroll
    for (int i = 0; i < NS1A; i++) mbar_init(bars + 8 * (BAR_EMPTYA + i), 4);
#pragma unroll
    for (int i = 0; i < NS1B; i++) mbar_init(bars + 8 * (BAR_EMPTYB + i), 2);
    asm volatile("fence.mbarrier_init.release.cluster;\n" ::: "memory");
  } else if (tid == 320) {
#pragma unroll
    for (int i = 0; i < NS2; i++) {
      mbar_init(bars + 8 * (BAR_FULL2 + i), 1);
      mbar_init(bars + 8 * (BAR_EMPTY2 + i), 4);
    }
    mbar_init(bars + 8 * BAR_DEAD, 2);
    mbar_init(bars + 8 * (BAR_DEAD + 1), 2);
    mbar_init(bars + 8 * BAR_X, 2);
    mbar_init(bars + 8 * BAR_REL, 2);
    asm volatile("fence.mbarrier_init.release.cluster;\n" ::: "memory");
  } else if (tid == 352) {
    mbar_init(bars + 8 * BAR_T, 1);
    mbar_init(bars + 8 * BAR_UH, 3);
    mbar_init(bars + 8 * BAR_LFREE, 4);
    mbar_init(bars + 8 * BAR_LAND, 1);
    mbar_init(bars + 8 * BAR_U, 1);
    mbar_init(bars + 8 * BAR_Q, 1);
    mbar_init(bars + 8 * BAR_STG, 9);
    asm volatile("fence.mbarrier_init.release.cluster;\n" ::: "memory");
  }
  if (warp == 8) PROF2(23);
  cluster_sync_all();
  if (warp == 8) PROF2(24);

  if (warp >= 8) {
    const int hw = warp - 8;
    const int lr = lane & 7, lm = lane >> 3;
    auto g1_issue_a = [&](int j, int s) {
      const uint32_t fb = bars + 8 * (BAR_FULLA + s);
      mbar_expect_tx(fb, STG1A);
      tma_load_3d_mc(sb + s * STG1A + rank * 16384, &tmX, fb, j * 64, par, gidx * 256 + rank * 128);
    };
    auto g1_issue_b = [&](int kb, int s) {
      const uint32_t fb = bars + 8 * (BAR_FULLB + s);
      mbar_expect_tx(fb, STG1B);
      tma_load_3d(sb + OFF_1B + s * STG1B, &tmW, fb, hp * 64, kb * 32, 0);
    };
    asm volatile("setmaxnreg.dec.sync.aligned.u32 %0;\n" :: "n"(REG_HELP));

    if (halo_cta) {
      if (hw == 0) {
        int s = 0, ph = 1;
#pragma unroll 1
        for (int kb = 0; kb < 16; kb++) {
          mbar_wait(bars + 8 * (BAR_EMPTYB + s), ph);
          const uint32_t fb = bars + 8 * (BAR_FULLB + s), st = sb + s * STGH;
          if (elect_one()) {
            mbar_expect_tx(fb, STGH);
            tma_load_4d(st, &tmXh, fb, kb * 64, 248, 0, 0);
            tma_load_3d(st + 8192, &tmWh, fb, 0, kb * 64, 16 + blockIdx.x * 4);
            tma_load_3d(st + 8192 + 32768, &tmWh, fb, 0, kb * 64, 32 + blockIdx.x * 4);
          }
          if (++s == 3) { s = 0; ph ^= 1; }
        }
      }
      __syncwarp();
    } else if (hw == 0) {
      uint32_t epoch = 0;
      if (lane < (MODE == 2 ? NS2 : 2)) mbar_arrive_cluster_n(mapa(bars, rank) + 8 * (BAR_EMPTY2 + lane), 4);
      if (MODE != 2) {
      epoch = ld_relaxed(g_flag_o + 2 * cta) + 1;
      if (lane == 0) {
        mbar_expect_tx(bars + 8 * BAR_U, 32768);
        mbar_expect_tx(bars + 8 * BAR_LAND, 32768 + 64);
        mbar_expect_tx(bars + 8 * BAR_Q, 32768);
        mbar_expect_tx(bars + 8 * BAR_T, T_END);
      }
      {
        int sa = 1, pha = 1, sbb = 2, phb = 1;
#pragma unroll 1
        for (int kb = 2; kb < 32; kb++) {
          if (!(kb & 1)) {
            mbar_wait(bars + 8 * (BAR_EMPTYA + sa), pha);
            if (elect_one()) g1_issue_a(kb >> 1, sa);
            if (++sa == NS1A) { sa = 0; pha ^= 1; }
          }
          mbar_wait(bars + 8 * (BAR_EMPTYB + sbb), phb);
          if (kb > 2 && elect_one()) g1_issue_b(kb, sbb);
          __syncwarp();
          if (kb >= PF0 && kb < PF0 + 12)
            prefetch_l2((kb < PF0 + 8 ? p.q + (size_t)chb * 16384 + (kb - PF0) * 2048 : p.wo + (size_t)chb * 8192 + (kb - PF0 - 8) * 2048) + lane * 64);
          if (kb == 4) PROF2(27);
          if (kb == 1) PROF2(38);
          if (kb == 2) PROF2(39);
          if (++sbb == NS1B) { sbb = 0; phb ^= 1; }
        }
      }
      static_assert(32 % NS1B == 2 && (32 / NS1B) % 2 == 0 && OFF_Q == OFF_1B && 2 * STG1B == 6 * 4096, "slots / parity of these loads");
      const uint8_t* tab = reinterpret_cast<const uint8_t*>(g_tab);
      if (lane == 0) {
        prefetch_tmap(&tmWo);
        prefetch_tmap(&tmQ);
        bulk_load(sb + OFF_T + T_A1, tab + T_A1, T_END - T_A1, bars + 8 * BAR_T);
        mbar_wait(bars + 8 * (BAR_EMPTYB + 2), 1);
        tma_load_5d(sb + OFF_Q + 6 * 4096, &tmQ, bars + 8 * BAR_Q, (chb & ~1) * 8, rank * 32 + 24);
        tma_load_5d(sb + OFF_Q + 7 * 4096, &tmQ, bars + 8 * BAR_Q, (chb & ~1) * 8, rank * 32 + 28);
        if (gidx != 0) wait_flag(g_flag_h + (hp >> 2), epoch);
      }
      __syncwarp();
      {
        uint4 hk0 = make_uint4(0, 0, 0, 0), hk1 = hk0, hv0 = hk0, hv1 = hk0;
        if (gidx != 0) {
          const uint4* src = g_halo + cta * 128 + lane;
          hk0 = __ldcg(src); hk1 = __ldcg(src + 32); hv0 = __ldcg(src + 64); hv1 = __ldcg(src + 96);
        }
        if (lane == 0) {
          mbar_wait(bars + 8 * (BAR_EMPTYB + 3), 1);
          bulk_load(sb + OFF_T, tab, T_TW, bars + 8 * BAR_T);
        }
        __syncwarp();
        PROF2(18);
        sts128(sb + OFF_L0 + lane * 16, hk0.x, hk0.y, hk0.z, hk0.w);
        sts128(sb + OFF_L0 + 512 + lane * 16, hk1.x, hk1.y, hk1.z, hk1.w);
        stsm4(sb + OFF_L0 + 1024 + lr * 128 + ((lm ^ lr) << 4), hv0.x, hv0.y, hv0.z, hv0.w);
        stsm4(sb + OFF_L0 + 1024 + lr * 128 + (((4 + lm) ^ lr) << 4), hv1.x, hv1.y, hv1.z, hv1.w);
        __syncwarp();
        if (lane == 0) {
          mbar_arrive(bars + 8 * BAR_STG);
          mbar_wait(bars + 8 * (BAR_EMPTYB + 4), 1);
          bulk_load(sb + OFF_T + T_TW, tab + T_TW, T_A1 - T_TW, bars + 8 * BAR_T);
          mbar_wait(bars + 8 * BAR_EMPTYB, 0);
#pragma unroll 1
          for (int i = 0; i < 6; i++) tma_load_5d(sb + OFF_Q + i * 4096, &tmQ, bars + 8 * BAR_Q, (chb & ~1) * 8, rank * 32 + i * 4);
        }
        __syncwarp();
      }
      }
      if (MODE != 1) {
        auto korder = [&](int i) { return MODE == 2 ? i : g2_k(hp, i); };
        const __nv_bfloat16* osrc = g_o + (size_t)(rb2 >> 1) * 16 * 16384 + ((rb2 & 1) * 2 + rank) * 4096;
        const uint32_t* flag = g_flag_o + (rb2 >> 1) * 32 + korder(lane & 15) * 2 + (rb2 & 1);
        uint32_t ready = MODE == 0 ? 0u : ~0u, pv = 0;
        auto look = [&]() {
          ready |= __ballot_sync(0xffffffffu, pv == epoch);
          asm volatile("fence.acquire.gpu;\n" ::: "memory");
          fence_async_all();
        };
        if (MODE == 0) {
          mbar_wait_idle(bars + 8 * BAR_REL, 0);
          if (POLL1) pv = ld_relaxed(flag);
          if (elect_one()) {
            mbar_expect_tx(bars + 8 * BAR_FULL2, STG2);
            tma_load_3d(sb + g2_b(0), &tmWo, bars + 8 * BAR_FULL2, 0, korder(0) * 64, cb2 * 2);
            tma_load_3d(sb + g2_b(1), &tmWo, bars + 8 * (BAR_FULL2 + 1), 0, korder(1) * 64, cb2 * 2);
          }
          if (POLL1) look();
        }
#pragma unroll
        for (int i = MODE == 0 ? 2 : 0; i < 16; i++) {
          const int kb = korder(i), s = i % NS2, ph = (i / NS2) & 1;
          const uint32_t fb = bars + 8 * (BAR_FULL2 + s);
          if (!((ready >> i) & 1)) {
            int n = 0;
            do {
              ready |= __ballot_sync(0xffffffffu, ld_acquire(flag) == epoch);
            } while (!((ready >> i) & 1) && ++n < SPIN_LIMIT);
            fence_async_all();
          }
          if (i == 2) PROF(21);
          mbar_wait(bars + 8 * (BAR_EMPTY2 + s), ph);
          if (elect_one()) {
            mbar_expect_tx(fb, STG2);
            asm volatile(
                "cp.async.bulk.shared::cluster.global.mbarrier::complete_tx::bytes.multicast::cluster [%0], [%1], %2, [%3], %4;\n"
                ::"r"(sb + g2_a(s) + rank * 8192), "l"(osrc + kb * 16384), "r"(8192), "r"(fb), "h"((uint16_t)3) : "memory");
            if (MODE != 0 || i >= 4) tma_load_3d(sb + g2_b(s), &tmWo, fb, 0, kb * 64, cb2 * 2);
          }
          if (MODE == 0 && i == LA0) pv = ld_relaxed(flag);
          if (MODE == 0 && i == LA1) look();
          if (i == 3) PROF(37);

        }
      }
      __syncwarp();
    } else if (MODE != 2) {
      {
        const int g = lane >> 2, t = lane & 3;
        uint32_t w[2][4];
#pragma unroll
        for (int h = 0; h < 2; h++) {
          const uint2 x = __ldg(reinterpret_cast<const uint2*>(p.shift_k + ((chb & ~1) * 8 + h * 8 + g) * 4));
          w[h][0] = __byte_perm(x.x, x.x, 0x1010);
          w[h][1] = __byte_perm(x.x, x.x, 0x3232);
          w[h][2] = __byte_perm(x.y, x.y, 0x1010);
          w[h][3] = __byte_perm(x.y, x.y, 0x3232);
        }
        auto swz = [](int r) { return (((r & 29) | ((r ^ (r >> 2)) & 2)) << 5) | (r & 16); };
        const uint32_t kring = sb + OFF_H + (hw - 1) * 8192, vring = kring + 4096;
        const int s0 = rank * 32 + (hw - 1) * 11, s1 = hw == 3 ? rank * 32 + 32 : s0 + 11;
        const size_t goff = (size_t)(lane >> 1) * DM + (chb & ~1) * 8 + (lane & 1) * 8;
        const __nv_bfloat16* kg = p.k + goff;
        const __nv_bfloat16* vg = p.v + goff;
        const uint32_t d0 = swz(lane >> 1) ^ ((lane & 1) << 4), d1 = swz(16 + (lane >> 1)) ^ ((lane & 1) << 4);
        auto issue = [&](int st) {
          const uint32_t so = (st & 3) << 10;
          cp_async16(kring + so + d0, kg + (size_t)st * 32 * DM, 16);
          cp_async16(kring + so + d1, kg + (size_t)(st * 32 + 16) * DM, 16);
          cp_async16(vring + so + d0, vg + (size_t)st * 32 * DM, 16);
          cp_async16(vring + so + d1, vg + (size_t)(st * 32 + 16) * DM, 16);
        };
        const int xa = 8 * (lr >> 1) + 2 * lm + (lr & 1), xb = 8 * (lr >> 1) - 4 + 2 * (lm & 1) + (lr & 1);
        const uint32_t la = swz(xa), lb = swz(xb & 31);
        const int backb = xb < 0 ? 1 : 0;
        const uint32_t ud[2] = {mapa(sb + OFF_U + g * 4096 + t * 16, 0), mapa(sb + OFF_U + g * 4096 + t * 16, 1)};
        const uint32_t ub[2] = {mapa(bars + 8 * BAR_U, 0), mapa(bars + 8 * BAR_U, 1)};
        if (lane == 0) mbar_wait(bars + 8 * (BAR_FULLB + NS1B - 1), 0);
        __syncwarp();
        if (lane >= 24) cp_async16(kring + (((s0 - 1) & 3) << 10) + d1, s0 > 0 ? kg + (size_t)(s0 * 32 - 16) * DM : kg, s0 > 0 ? 16 : 0);
        issue(s0);
        asm volatile("cp.async.commit_group;\n" ::: "memory");
        issue(s0 + 1);
        asm volatile("cp.async.commit_group;\n" ::: "memory");
#pragma unroll 1
        for (int st = s0; st < s1; st++) {
          if (st + 2 < s1) issue(st + 2);
          if (hw == 1 && st - s0 < 8) prefetch_l2(p.ssm_k + (size_t)(chb * 8 + st - s0) * SEQ + lane * 64);
          if (hw == 2 && st == s0 + 4 && lane < 2) prefetch_l2(g_tab + (chb * 2 + lane) * 32);
          const uint32_t uo = (st ^ ((g ^ (st >> 2)) & 1)) * 64;
          asm volatile("cp.async.commit_group;\n" ::: "memory");
          asm volatile("cp.async.wait_group 2;\n" ::: "memory");
          __syncwarp();
#pragma unroll
          for (int h = 0; h < 2; h++) {
            uint32_t e[6], vv[4], e4[4];
            ldsm4t(e4, kring + ((st & 3) << 10) + (la ^ (h << 4)));
            ldsm2t(e[0], e[1], kring + (((st - backb) & 3) << 10) + (lb ^ (h << 4)));
            ldsm4t(vv, vring + ((st & 3) << 10) + (la ^ (h << 4)));
            e[2] = e4[0]; e[3] = e4[1]; e[4] = e4[2]; e[5] = e4[3];
            uint32_t o[5];
#pragma unroll
            for (int i = 0; i < 5; i++) o[i] = __byte_perm(e[i], e[i + 1], 0x5432);
#pragma unroll
            for (int i = 0; i < 4; i++) {
              uint32_t a = bmul2(o[i], w[h][3]);
              a = bfma2(e[i + 1], w[h][2], a);
              a = bfma2(o[i + 1], w[h][1], a);
              a = bfma2(e[i + 2], w[h][0], a);
              vv[i] = bmul2(a, vv[i]);
            }
            st_async128(ud[h] + uo, ub[h], vv[0], vv[1], vv[2], vv[3]);
          }
          __syncwarp();
        }
        PROF(16);
      }
      {
        const int rw = (lane >> 3) + (lane & 4), ck = lane & 3;
        const uint32_t so = rw * 64 + ck * 16, dof = rw * 128 + ((ck ^ rw) << 4);
        const uint8_t* hsrc = reinterpret_cast<const uint8_t*>(p.ssm_k + (size_t)chb * 8 * SEQ) + so;
        const float dv = lane < 8 ? __bfloat162float(p.ssm_D[chb * 8 + lane]) : 0.f;
        uint32_t x[32];
        auto load = [&](const uint8_t* src, int i) {
          asm volatile("ld.v4.u32 {%0,%1,%2,%3}, [%4];\n" : "=r"(x[4 * i]), "=r"(x[4 * i + 1]), "=r"(x[4 * i + 2]), "=r"(x[4 * i + 3])
                       : "l"(src + i * 512) : "memory");
        };
#pragma unroll
        for (int i = 0; i < 8; i++) load(hsrc + (hw - 1) * 4096, i);
        nb_sync(NB_HELP3, 96);
        mbar_wait(bars + 8 * BAR_U, 0);
        int eh = 0;
#pragma unroll 1
        for (int n = 2 * (hw - 1); n < 16; n += (n & 1) ? 5 : 1) {
          const int c = n >> 1;
          const uint8_t* nsrc = (n & 1) ? hsrc + (c < 5 ? c + 3 : c) * 4096
                                        : smem - OFF_L0 + OFF_U + c * 4096 + (so ^ (((c ^ (lane >> 2)) & 1) << 6));
          const uint32_t dst = sb + ((n & 1) ? OFF_U : OFF_H) + c * 4096 + dof;
          const float dc = __shfl_sync(0xffffffffu, dv, c);
          const float h0 = bf_lo(x[0]) + ((lane | (n & 1)) == 0 ? dc : 0.f), h1 = bf_hi(x[0]);
          x[0] = pack_bf16(h0, h1);
          uint32_t m[2] = {x[0], x[1]};
#pragma unroll
          for (int i = 2; i < 32; i++) asm("max.xorsign.abs.bf16x2 %0, %0, %1;\n" : "+r"(m[i & 1]) : "r"(x[i]));
          asm("max.xorsign.abs.bf16x2 %0, %0, %1;\n" : "+r"(m[0]) : "r"(m[1]));
          const uint32_t e = max(__reduce_max_sync(0xffffffffu, max((m[0] >> 7) & 255u, (m[0] >> 23) & 255u)), 5u);
          const uint32_t sc = (259u - e) * 0x00800080u;
#pragma unroll
          for (int i = 0; i < 8; i++) {
            uint32_t o[4];
#pragma unroll
            for (int j = 0; j < 4; j++) {
              const uint32_t v = bmul2(x[4 * i + j], sc);
              asm("cvt.rn.f16x2.f32 %0, %1, %2;\n" : "=r"(o[j]) : "f"(bf_hi(v)), "f"(i + j == 0 ? h0 * bf_hi(sc) : bf_lo(v)));
            }
            sts128((dst + (i & 3) * 1024) ^ ((i >> 2) << 6), o[0], o[1], o[2], o[3]);
            load(nsrc, i);
          }
          if (n & 1) {
            const int f = min(max((int)e + eh - 129, 0), 254);
            if (lane < 2)
              asm volatile("st.async.weak.shared::cluster.mbarrier::complete_tx::bytes.b32 [%0], %2, [%1];\n"
                           ::"r"(mapa(sb + OFF_SC + rank * 32 + c * 4, lane)), "r"(mapa(bars + 8 * BAR_LAND, lane)), "r"(f << 7) : "memory");
          }
          eh = e;
        }
        fence_async_smem();
        __syncwarp();
        if (lane == 0) mbar_arrive(bars + 8 * BAR_UH);
        PROF(32);
      }
      if (hw < 3) {
        const uint32_t rb = mapa(bars, lane & 1);
        const uint32_t epoch = ld_relaxed(g_flag_o + 2 * cta + hw - 1) + 1;
        const bool own = hw - 1 == (rb2 & 1);
        nb_sync(NB_OREADY + hw - 1, 160);
        if (lane == 0) {
          asm volatile("cp.async.bulk.global.shared::cta.bulk_group [%0], [%1], %2;\n" ::"l"(g_o + (size_t)cta * 16384 + (hw - 1) * 8192),
                       "r"(sb + OFF_OP + (own ? 16384 : 0)), "r"(16384) : "memory");
          bulk_commit();
        }
        if (lane < 2) {
          mbar_arrive_cluster(rb + 8 * (BAR_EMPTY2 + 2));
          mbar_arrive_cluster(rb + 8 * (BAR_EMPTY2 + 3));
        }
        if (lane == 0) {
          bulk_wait0();
          if (own) mbar_expect_tx(bars + 8 * (BAR_FULL2 + 1), 16384);
          mbar_arrive_cluster(mapa(bars, own ? rank : rank ^ 1) + 8 * BAR_X);
          st_release(g_flag_o + 2 * cta + hw - 1, epoch);
          mbar_arrive(bars + 8 * BAR_REL);
        }
        __syncwarp();
        PROF(own ? 17 : 19);
      } else {
        if (MODE == 0) {
          mbar_wait_idle(bars + 8 * BAR_X, 0);
          if (elect_one())
            asm volatile("cp.async.bulk.shared::cluster.shared::cta.mbarrier::complete_tx::bytes [%0], [%1], %2, [%3];\n"
                         ::"r"(mapa(sb + OFF_OP, rank ^ 1)), "r"(sb + OFF_OP + 16384), "r"(16384),
                         "r"(mapa(bars + 8 * BAR_FULL2, rank ^ 1)) : "memory");
        }
        if (MODE == 0) {
          mbar_wait_idle(bars + 8 * BAR_DEAD, 0);
          if (elect_one()) {
            tma_load_3d(sb + g2_b(2), &tmWo, bars + 8 * (BAR_FULL2 + 2), 0, g2_k(hp, 2) * 64, cb2 * 2);
            tma_load_3d(sb + g2_b(3), &tmWo, bars + 8 * (BAR_FULL2 + 3), 0, g2_k(hp, 3) * 64, cb2 * 2);
          }
        }
        __syncwarp();
      }
      {
        const int c8 = (4 * (lr >> 1) + 2 * (lm & 1) + (lr & 1)) & 7;
        const bool own = (lr >> 2) == rank;
        const uint32_t ya = sb + (own ? y_slot(c8 & 1, c8 >> 1) : OFF_LAND + c8 * 2048);
        const uint32_t yx = ((lm >> 1) ^ lr) << 4;
        const int row = (lane >> 4) * 8 + ((lane >> 3) & 1) * 16 + ((lane >> 2) & 1);
        uint2* og = reinterpret_cast<uint2*>(p.out + (size_t)(rank * 1024 + row) * (2 * DM) + (chb & ~1) * 8 + (lane & 3) * 4);
        const uint32_t qa = sb + OFF_Q + (lane >> 4) * 512 + (lane & 15) * 8;
        mbar_wait(bars + 8 * BAR_Q, 0);
        mbar_wait_idle(bars + 8 * BAR_LAND, 0);
        PROF(33);
        const uint32_t t0 = clock();
        const uint4 s4 = lds128(sb + OFF_SC + (lane & 3) * 16);
        const uint32_t sc[2] = {s4.x | (s4.y << 16), s4.z | (s4.w << 16)};
        auto fin = [&](uint32_t q2, uint32_t y2, uint32_t s2) {
          float lo, hi;
          asm("{\n.reg .b16 l, h;\nmov.b32 {l, h}, %2;\ncvt.f32.f16 %0, l;\ncvt.f32.f16 %1, h;\n}\n" : "=f"(lo), "=f"(hi) : "r"(y2));
          return bmul2(q2, bmul2(pack_bf16(lo, hi), s2));
        };
#pragma unroll 1
        for (int j = hw - 1; j < 16; j += 3) {
          uint32_t y[4][4];
          uint2 q[8];
          while ((uint32_t)clock() - t0 < j * PACE) __nanosleep(40);
          const uint32_t qj = qa + j * 2048;
#pragma unroll
          for (int i = 0; i < 4; i++) ldsm4t(y[i], ya + j * 128 + (yx ^ (i << 5)));
#pragma unroll
          for (int i = 0; i < 8; i++) q[i] = lds64(qj + (i >> 2) * 1024 + (i & 3) * 128);
#pragma unroll
          for (int i = 0; i < 8; i++) {
            og[(size_t)(j * 64 + (i >> 2) * 32 + (i & 3) * 2) * (2 * DM / 4)] =
                make_uint2(fin(q[i].x, y[i >> 1][2 * (i & 1)], sc[0]), fin(q[i].y, y[i >> 1][2 * (i & 1) + 1], sc[1]));
            if (i < 7) asm volatile("nanosleep.u32 %0;\n" ::"r"(FINE) : "memory");
          }
        }
      }
      PROF(22);
    }
    cluster_sync_all();
  } else {
    asm volatile("setmaxnreg.inc.sync.aligned.u32 %0;\n" :: "n"(REG_MATH));
    if (warp == 0) PROF2(26);
    const int wg = warp >> 2;
    const int wtid = tid & 127;
    const bool signaller = (wtid == 0) || (wtid == 32);
    const uint32_t rbars = mapa(bars, wtid >> 5 & 1);

    if (halo_cta) {
      const uint32_t epoch = ld_relaxed(g_flag_h + blockIdx.x) + 1;
      float acc0[64], acc1[64];
      int s = 0, ph = 0;
#pragma unroll 1
      for (int kb = 0; kb < 16; kb++) {
        mbar_wait(bars + 8 * (BAR_FULLB + s), ph);
        const uint32_t st = sb + s * STGH;
        const uint64_t da = mkdesc(st, 16, 1024, 1);
        const uint64_t db = mkdesc(st + 8192 + wg * 32768, 8192, 1024, 1);
        wg_fence();
#pragma unroll
        for (int kk = 0; kk < 4; kk++) {
          wgmma_n128(acc0, da + 2 * kk, db + 128 * kk, kb + kk);
          wgmma_n128(acc1, da + 2 * kk, db + 1024 + 128 * kk, kb + kk);
        }
        wg_commit();
        wg_wait<0>();
        if (wtid == 0) mbar_arrive(bars + 8 * (BAR_EMPTYB + s));
        if (++s == 3) { s = 0; ph ^= 1; }
      }
      fence_regs(acc0);
      fence_regs(acc1);
      if ((warp & 3) != 3) {
#pragma unroll
        for (int hh = 0; hh < 2; hh++) {
          uint4* dst = g_halo + ((hh * 4 + (warp & 3) + 1) * 16 + blockIdx.x * 4) * 128 + wg * 64 + lane;
#pragma unroll
          for (int j = 0; j < 4; j++) {
            const int o = 16 * j + 2 * hh;
            dst[(j >> 1) * 128 + (j & 1) * 32] =
                make_uint4(pack_bf16(acc0[o], acc0[o + 1]), pack_bf16(acc0[o + 4], acc0[o + 5]),
                           pack_bf16(acc0[o + 8], acc0[o + 9]), pack_bf16(acc0[o + 12], acc0[o + 13]));
            dst[(2 + (j >> 1)) * 128 + (j & 1) * 32] =
                make_uint4(pack_bf16(acc1[o], acc1[o + 1]), pack_bf16(acc1[o + 4], acc1[o + 5]),
                           pack_bf16(acc1[o + 8], acc1[o + 9]), pack_bf16(acc1[o + 12], acc1[o + 13]));
          }
        }
      }
      nb_sync(NB_G1DONE, 256);
      if (tid == 0) st_release(g_flag_h + blockIdx.x, epoch);
      PROF(36);
      cluster_sync_all();
      return;
    }

    float acc[64];
    auto g2_step = [&](int s, int kb) {
      const uint64_t da = mkdesc(sb + g2_a(s) + wg * 8192, 16, 1024, 1);
      const uint64_t db = mkdesc(sb + g2_b(s), 8192, 1024, 1);
      wg_fence();
      wgmma_n128(acc, da, db, kb);
      wgmma_n128(acc, da + 2, db + 128, 1);
      wgmma_n128(acc, da + 4, db + 256, 1);
      wgmma_n128(acc, da + 6, db + 384, 1);
      wg_commit();
    };

    if (MODE != 2) {
    uint32_t a1[2][4], tw[16], d1[32];
    const uint32_t tb = sb + OFF_T + wtid * 16;
    const uint64_t dx = mkdesc(sb + OFF_U + wg * 4096, OFF_H - OFF_U, 1024, 1);
    auto s1 = [&](int it) {
      hmma_n128t<0>(d1, a1[0], dx + it * 512);
      hmma_n128t<1>(d1, a1[1], dx + it * 512 + 128);
      wg_commit();
    };
    auto ldtw = [&](int i) {
      const uint4 v = lds128(tb + T_TW + i * 2048);
      tw[4 * i] = v.x; tw[4 * i + 1] = v.y; tw[4 * i + 2] = v.z; tw[4 * i + 3] = v.w;
    };
    {
      float acc0[96], acc1[96];
      int sa = 0, pha = 0, sbb = 0, phb = 0;
      asm volatile("cp.async.wait_group 0;\n" ::: "memory");
      fence_async_smem();
      nb_sync(NB_FIRST, 256);
      if (tid == 0) {
        mbar_arrive(bars + 8 * BAR_FULLA);
        mbar_arrive(bars + 8 * BAR_FULLB);
      }
      PROF(0 + wg);
#pragma unroll 1
      for (int kb = 0; kb < 30; kb++) {
        if (!(kb & 1)) mbar_wait(bars + 8 * (BAR_FULLA + sa), pha);
        mbar_wait(bars + 8 * (BAR_FULLB + sbb), phb);
        if (kb == 0) PROF2(0 + wg);
        if (kb == 4 && wg == 0) PROF2(28);
        if (kb == 8 && wg == 0) PROF2(29);
        if (kb == 16 && wg == 0) PROF2(30);
        const uint64_t da = mkdesc(sb + sa * STG1A + wg * 16384 + (kb & 1) * 64, 16, 1024, 1);
        const uint64_t db = mkdesc(sb + OFF_1B + sbb * STG1B, 4096, 1024, 1);
        wg_fence();
        wgmma_n192(acc0, da, db, kb);
        wgmma_n192(acc1, da + 512, db, kb);
        wgmma_n192(acc0, da + 2, db + 128, 1);
        wgmma_n192(acc1, da + 514, db + 128, 1);
        wg_commit();
        wg_wait<1>();
        if (kb > 0) {
          if (wtid == 64) mbar_arrive(bars + 8 * (BAR_EMPTYB + (sbb == 0 ? NS1B - 1 : sbb - 1)));
          if (!(kb & 1) && signaller) mbar_arrive_cluster(rbars + 8 * (BAR_EMPTYA + (sa == 0 ? NS1A - 1 : sa - 1)));
        }
        if (++sbb == NS1B) { sbb = 0; phb ^= 1; }
        if ((kb & 1) && ++sa == NS1A) { sa = 0; pha ^= 1; }
      }
      const int blk0 = wg * 8 + (warp & 3);
      const int lr = lane & 7, lm = lane >> 3;
      const bool le0 = 2 * (lane & 3) <= (lane >> 2), le1 = 2 * (lane & 3) + 1 <= (lane >> 2);
      const uint32_t maskLE = (le0 ? 0x0000FFFFu : 0u) | (le1 ? 0xFFFF0000u : 0u);
      uint32_t k0[2][2][4], k1[2][2][4], qa[2][2][8];
      float l[2][2][4];
      {
        static_assert(15 % NS1A == 0 && 30 % NS1B == 0, "slots of the last k blocks");
        mbar_wait(bars + 8 * BAR_FULLA, 1);
        mbar_wait(bars + 8 * BAR_FULLB, 0);
        mbar_wait(bars + 8 * (BAR_FULLB + 1), 0);
        const uint64_t da = mkdesc(sb + wg * 16384, 16, 1024, 1);
        const uint64_t db = mkdesc(sb + OFF_1B, 4096, 1024, 1);
        wg_fence();
#pragma unroll
        for (int i = 0; i < 4; i++) wgmma_n192(acc0, da + 2 * i, db + (i >> 1) * (STG1B >> 4) + (i & 1) * 128, 1);
        wg_commit();
        wg_wait<1>();
        if (wtid == 64) mbar_arrive(bars + 8 * (BAR_EMPTYB + NS1B - 1));
#pragma unroll
        for (int i = 0; i < 2; i++) wgmma_n192(acc1, da + 512 + 2 * i, db + (i >> 1) * (STG1B >> 4) + (i & 1) * 128, 1);
        wg_commit();
        wg_wait<1>();
        fence_regs(acc0);
        attn_stage(sb, blk0, lane, acc0, k1[0]);
#pragma unroll
        for (int i = 2; i < 4; i++) wgmma_n192(acc1, da + 512 + 2 * i, db + (i >> 1) * (STG1B >> 4) + (i & 1) * 128, 1);
        wg_commit();
        attn_pack(acc0, qa[0], k0[0]);
        wg_wait<0>();
        fence_regs(acc1);
      }
      if (wtid == 64) mbar_arrive(bars + 8 * BAR_EMPTYB);
      PROF(2 + wg);
      attn_stage(sb, blk0 + 4, lane, acc1, k1[1]);
      __syncwarp();
      if (lane == 0) mbar_arrive(bars + 8 * BAR_STG);
      mbar_wait(bars + 8 * BAR_U, 0);
      attn_pack(acc1, qa[1], k0[1]);
      attn_own(k0[0], k1[0], le0, le1, qa[0], l[0]);
      attn_own(k0[1], k1[1], le0, le1, qa[1], l[1]);
      static_assert(OFF_L0 + 2048 == OFF_VP, "halo V rows");
      const uint32_t vl0 = sb + OFF_VP - 1024 + blk0 * 2048 + (lm >> 1) * 1024 + lr * 128 + (((lm & 1) ^ lr) << 4);
      const uint32_t vl[4] = {vl0, vl0 ^ 64, vl0 ^ 32, vl0 ^ 96};
      const uint32_t obase = sb + OFF_OP + (wg == (rb2 & 1) ? 16384 : 0) + ((warp & 3) * 16 + lr) * 128 + ((lm ^ lr) << 4);
      mbar_wait(bars + 8 * BAR_STG, 0);
      {
        uint32_t km[4][4], va[8][4], vb[8][4], pp[8];
        float x[8][2];
#pragma unroll
        for (int n = 0; n < 4; n++) {
          const int blk = blk0 + 4 * (n >> 1);
          to_arr(km[n], lds128(sb + (blk == 0 ? OFF_L0 : OFF_KH + (blk - 1) * 2048) + (n & 1) * 512 + lane * 16));
        }
#pragma unroll
        for (int n = 0; n < 8; n++) {
          const uint32_t o = ((n >> 1) & 1) * 8192 + (n >> 2) * 1024;
          ldsm4t(va[n], vl[n & 1] + o);
          ldsm4t(vb[n], vl[2 + (n & 1)] + o);
        }
        const bool first = blk0 == 0 && gidx == 0;
#pragma unroll
        for (int n = 0; n < 4; n++) {
          const uint32_t(&q)[8] = qa[n >> 1][n & 1];
          float sm[4];
          mma16816_z(sm, q[0], q[1], q[2], q[3], km[n][0], km[n][1]);
          mma16816(sm, q[4], q[5], q[6], q[7], km[n][2], km[n][3]);
          if (n < 2 && first) sm[0] = sm[1] = -1e9f / 0.17677669529663687f;
          x[n][0] = le0 ? l[n >> 1][n & 1][0] : sm[0];
          x[n][1] = le1 ? l[n >> 1][n & 1][1] : sm[1];
          x[4 + n][0] = l[n >> 1][n & 1][2];
          x[4 + n][1] = l[n >> 1][n & 1][3];
        }
        quad_softmax<8>(x, pp);
#pragma unroll
        for (int n = 7; n >= 0; n--)
          attn_pv((obase ^ ((n & 1) << 6)) + ((n >> 1) & 1) * 8192 + (n >> 2) * 1024, va[n], vb[n], pp[n], maskLE);
      }
      fence_async_smem();
      nb_arrive(NB_OREADY + wg, 160);
    }

    {
      const int w = warp & 3;
      uint32_t a4[8][4];
      uint32_t d4[16];
      PROF(34 + wg);
      const uint64_t dz = mkdesc(sb + OFF_U + wg * 4096, 1024, 128, 0);
      const uint64_t db2 = mkdesc(sb + OFF_T + T_B2, 128, 256, 0);
      mbar_wait(bars + 8 * BAR_T, 0);
      mbar_wait(bars + 8 * BAR_UH, 0);
      to_arr(a1[0], lds128(tb + T_A1));
      to_arr(a1[1], lds128(tb + T_A1 + 2048));
      wg_fence();
      s1(0);
      ldtw(0);
      ldtw(1);
      const uint32_t za = sb + (w < 2 ? OFF_U : OFF_H) + wg * 4096 + (w & 1) * 8192 + lane * 16;
      const uint32_t yl = (wtid ^ (4 * rank + wg)) * 16;
      const uint32_t yown = mapa(sb, rank) + yl, yrem = mapa(sb + OFF_LAND + wg * 2048, rank ^ 1) + yl;
      const uint32_t yb[2] = {mapa(bars + 8 * BAR_LAND, 0), mapa(bars + 8 * BAR_LAND, 1)};
      wg_wait<0>();
      fence_regs(d1);
      auto s4 = [&]() {
        wg_fence();
#pragma unroll
        for (int ks = 0; ks < 8; ks++) {
          const uint64_t d = dz + (ks & 1) * 128 + ((ks >> 1) & 1) * 512 + (ks >> 2) * ((OFF_H - OFF_U) >> 4);
          if (ks == 0) hmma_n64t<0>(d4, a4[ks], d);
          else hmma_n64t<1>(d4, a4[ks], d);
        }
        wg_commit();
      };
      auto e4 = [&](int pr) {
        fence_regs(d4);
        mbar_wait(bars + 8 * (pr == 0 ? BAR_LFREE : BAR_DEAD + 1), 0);
#pragma unroll
        for (int u = 0; u < 2; u++) {
          const int it = 2 * pr + u;
          const uint32_t o = (yown + y_slot(wg, it)) ^ (pr << 5), m = (yrem + it * 4096) ^ (pr << 5);
          st_async128(rank ? m : o, yb[0], d4[8 * u], d4[8 * u + 1], d4[8 * u + 2], d4[8 * u + 3]);
          st_async128(rank ? o : m, yb[1], d4[8 * u + 4], d4[8 * u + 5], d4[8 * u + 6], d4[8 * u + 7]);
        }
      };
      uint32_t a2[2][2][2][4], a3[2][2][4], d2[2][2][8], d3[2][8];
      auto s2a = [&]() {
        wg_fence();
#pragma unroll
        for (int c = 0; c < 4; c++) hmma_n32<0, 0>(d2[c & 1][c >> 1], a2[0][c & 1][c >> 1], db2 + (c >> 1) * 128);
      };
      auto s2b = [&]() {
        wg_fence();
#pragma unroll
        for (int c = 0; c < 4; c++) {
          hmma_n32<1, 0>(d2[c & 1][c >> 1], a2[1][c & 1][c >> 1], db2 + (c >> 1) * 128 + 64);
          if (c & 1) wg_commit();
        }
      };
      fft_e1<0>(d1, tw, a2[0]);
      s2a();
      fft_e1<1>(d1, tw, a2[1]);
      s2b();
      s1(1);
      ldtw(2);
      ldtw(3);
#pragma unroll
      for (int i = 0; i < 8; i++) to_arr(a4[i], lds128(tb + T_A4 + i * 2048));
#pragma unroll
      for (int it = 0; it < 4; it++) {
        if (it == 2) wg_wait<3>(); else if (it == 3) wg_wait<1>(); else wg_wait<2>();
        fence_regs(d2[0][0]);
        fence_regs(d2[1][0]);
        fft_e2<0, 0>(d2[0][0], d2[1][0], a3[0]);
        fft_e2<0, 1>(d2[0][0], d2[1][0], a3[1]);
        if (it == 2) wg_wait<2>(); else if (it == 3) wg_wait<0>(); else wg_wait<1>();
        fence_regs(d2[0][1]);
        fence_regs(d2[1][1]);
        fft_e2<1, 0>(d2[0][1], d2[1][1], a3[0]);
        fft_e2<1, 1>(d2[0][1], d2[1][1], a3[1]);
        wg_fence();
        hmma_n32<0, 0>(d3[0], a3[0][0], db2);
        hmma_n32<0, 0>(d3[1], a3[0][1], db2);
        hmma_n32<1, 0>(d3[0], a3[1][0], db2 + 64);
        hmma_n32<1, 0>(d3[1], a3[1][1], db2 + 64);
        wg_commit();
        if (it < 3) {
          wg_wait<1>();
          if (it == 2) {
            if (wtid == 64) mbar_arrive(bars + 8 * BAR_DEAD);
            e4(0);
          }
          fence_regs(d1);
          fft_e1<0>(d1, tw, a2[0]);
        }
        wg_wait<0>();
        if (it == 3 && wtid == 64) mbar_arrive(bars + 8 * (BAR_DEAD + 1));
        fence_regs(d3[0]);
        fence_regs(d3[1]);
        if (it < 3) s2a();
        fft_e3(d3, tw, za + (it & 1) * 512);
        if (it < 3) {
          fft_e1<1>(d1, tw, a2[1]);
          s2b();
        }
        if (it & 1) {
          fence_async_smem();
          nb_sync(NB_WG + wg, 128);
          if (it == 1 && signaller) mbar_arrive_cluster(rbars + 8 * BAR_LFREE);
          s4();
        }
        if (it < 2) s1(it + 2);
        if (w == 0) PROF3(40 + 4 * wg + it);
      }
      if (PEEL && MODE == 0) {
        mbar_wait(bars + 8 * BAR_FULL2, 0);
        g2_step(0, 0);
        wg_wait<1>();
      } else {
        wg_wait<0>();
      }
      if (signaller) mbar_arrive_cluster(rbars + 8 * (BAR_EMPTY2 + 4));
      e4(1);
      if (PEEL && MODE == 0) {
        wg_wait<0>();
        if (signaller) mbar_arrive_cluster(rbars + 8 * BAR_EMPTY2);
      }
      PROF(6 + wg);
    }
    }

    if (MODE != 1) {
      int s = PEEL && MODE == 0, ph = 0;
#pragma unroll 1
      for (int kb = s; kb < STAG; kb++) {
        mbar_wait(bars + 8 * (BAR_FULL2 + s), ph);
        if (kb == 1) PROF(8 + wg);
        if (warp == 4) PROF2(40 + kb);
        g2_step(s, kb);
        wg_wait<0>();
        if (kb < 16 - NS2 && signaller) mbar_arrive_cluster(rbars + 8 * (BAR_EMPTY2 + s));
        if (++s == NS2) { s = 0; ph ^= 1; }
      }
      if (STAG < 16) {
        if (wg == LAST) nb_sync(NB_LEAD, 256);
#pragma unroll
        for (int kb = STAG; kb < 16; kb++) {
          mbar_wait(bars + 8 * (BAR_FULL2 + kb % NS2), (kb / NS2) & 1);
          g2_step(kb % NS2, 1);
        }
        if (wg != LAST) nb_arrive(NB_LEAD, 256);
      }
      wg_wait<0>();
      fence_regs(acc);
      PROF(10 + wg);
      const int lr = lane & 7, lm = lane >> 3;
      const uint32_t wbase = sb + warp * 2048;
      const uint32_t base = wbase + (lr + 8 * (lm & 1)) * 128;
#pragma unroll
      for (int j = 0; j < 16; j += 2) {
        const uint32_t a = base + (j >> 3) * 16384 + ((((j & 7) + (lm >> 1)) ^ lr) << 4);
        stsm4(a, pack_bf16(acc[4 * j], acc[4 * j + 1]), pack_bf16(acc[4 * j + 2], acc[4 * j + 3]),
              pack_bf16(acc[4 * j + 4], acc[4 * j + 5]), pack_bf16(acc[4 * j + 6], acc[4 * j + 7]));
      }
      __syncwarp();
      {
        const int rr = lane >> 4, ck = lane & 7, hf = (lane >> 3) & 1;
        uint4* og = reinterpret_cast<uint4*>(p.out + (size_t)(2 * ((rb2 & 7) * 128 + warp * 16 + rr) + (rb2 >> 3)) * (2 * DM) + DM + cb2 * 128 + hf * 64 + ck * 8);
        uint4 v[8];
#pragma unroll
        for (int i = 0; i < 8; i++) v[i] = lds128(wbase + hf * 16384 + (2 * i + rr) * 128 + ((ck ^ ((2 * i + rr) & 7)) << 4));
#pragma unroll
        for (int i = 0; i < 8; i++) og[(size_t)i * 4 * (2 * DM / 8)] = v[i];
      }
      PROF(12 + wg);
    }
    cluster_sync_all();
  }
}

typedef CUresult (*EncodeFn)(CUtensorMap*, CUtensorMapDataType, cuuint32_t, void*, const cuuint64_t*, const cuuint64_t*,
                             const cuuint32_t*, const cuuint32_t*, CUtensorMapInterleave, CUtensorMapSwizzle,
                             CUtensorMapL2promotion, CUtensorMapFloatOOBfill);

void make_map(EncodeFn enc, CUtensorMap* tm, const void* base, int rank, const cuuint64_t* dims, const cuuint64_t* strides,
              const cuuint32_t* box, CUtensorMapSwizzle swz) {
  cuuint32_t es[5] = {1, 1, 1, 1, 1};
  enc(tm, CU_TENSOR_MAP_DATA_TYPE_BFLOAT16, rank, const_cast<void*>(base), dims, strides, box, es,
      CU_TENSOR_MAP_INTERLEAVE_NONE, swz, CU_TENSOR_MAP_L2_PROMOTION_L2_256B, CU_TENSOR_MAP_FLOAT_OOB_FILL_NONE);
}

}

extern "C" void kernel_launch(void* const* d_in, const int* in_sizes, int n_in, void* d_out, int out_size) {
  static EncodeFn enc = nullptr;
  static bool coresident = true;
  if (!enc) {
    void* fn = nullptr;
    cudaDriverEntryPointQueryResult qr;
    cudaGetDriverEntryPoint("cuTensorMapEncodeTiled", &fn, cudaEnableDefault, &qr);
    enc = (EncodeFn)fn;
    cudaFuncSetAttribute(fused_kernel<0>, cudaFuncAttributeMaxDynamicSharedMemorySize, SMEM_BYTES);
    cudaFuncSetAttribute(fused_kernel<1>, cudaFuncAttributeMaxDynamicSharedMemorySize, SMEM_BYTES);
    cudaFuncSetAttribute(fused_kernel<2>, cudaFuncAttributeMaxDynamicSharedMemorySize, SMEM_BYTES);
    cudaLaunchConfig_t cfg = {};
    cfg.gridDim = dim3(NCTA);
    cfg.blockDim = dim3(NTHREADS);
    cfg.dynamicSmemBytes = SMEM_BYTES;
    cudaLaunchAttribute at;
    at.id = cudaLaunchAttributeClusterDimension;
    at.val.clusterDim.x = 2;
    at.val.clusterDim.y = 1;
    at.val.clusterDim.z = 1;
    cfg.attrs = &at;
    cfg.numAttrs = 1;
    int nclusters = 0;
    if (cudaOccupancyMaxActiveClusters(&nclusters, fused_kernel<0>, &cfg) == cudaSuccess) coresident = nclusters >= NCTA / 2;
    (void)cudaGetLastError();
  }
  CUtensorMap tmX, tmW, tmWo, tmQ, tmXh, tmWh;
  {
    cuuint64_t dims[3] = {1024, 2, 1024};
    cuuint64_t str[2] = {2048, 4096};
    cuuint32_t box[3] = {64, 1, 128};
    make_map(enc, &tmX, d_in[6], 3, dims, str, box, CU_TENSOR_MAP_SWIZZLE_128B);
  }
  {
    cuuint64_t dims[3] = {1024, 1024, 3};
    cuuint64_t str[2] = {6144, 2048};
    cuuint32_t box[3] = {64, 32, 3};
    make_map(enc, &tmW, d_in[7], 3, dims, str, box, CU_TENSOR_MAP_SWIZZLE_128B);
  }
  {
    cuuint64_t dims[3] = {64, 1024, 16};
    cuuint64_t str[2] = {2048, 128};
    cuuint32_t box[3] = {64, 64, 2};
    make_map(enc, &tmWo, d_in[8], 3, dims, str, box, CU_TENSOR_MAP_SWIZZLE_128B);
  }
  {
    cuuint64_t dims[5] = {1024, 2, 2, 8, 64};
    cuuint64_t str[4] = {2048, 16 * 2048, 2 * 2048, 32 * 2048};
    cuuint32_t box[5] = {16, 2, 2, 8, 4};
    make_map(enc, &tmQ, d_in[0], 5, dims, str, box, CU_TENSOR_MAP_SWIZZLE_NONE);
  }
  {
    cuuint64_t dims[4] = {1024, 256, 2, 4};
    cuuint64_t str[3] = {4096, 2048, 256 * 4096};
    cuuint32_t box[4] = {64, 8, 2, 4};
    make_map(enc, &tmXh, d_in[6], 4, dims, str, box, CU_TENSOR_MAP_SWIZZLE_128B);
  }
  {
    cuuint64_t dims[3] = {64, 1024, 48};
    cuuint64_t str[2] = {6144, 128};
    cuuint32_t box[3] = {64, 64, 4};
    make_map(enc, &tmWh, d_in[7], 3, dims, str, box, CU_TENSOR_MAP_SWIZZLE_128B);
  }
  Params p;
  p.q = (const __nv_bfloat16*)d_in[0];
  p.k = (const __nv_bfloat16*)d_in[1];
  p.v = (const __nv_bfloat16*)d_in[2];
  p.shift_k = (const __nv_bfloat16*)d_in[3];
  p.ssm_k = (const __nv_bfloat16*)d_in[4];
  p.ssm_D = (const __nv_bfloat16*)d_in[5];
  p.x = (const __nv_bfloat16*)d_in[6];
  p.w = (const __nv_bfloat16*)d_in[7];
  p.wo = (const __nv_bfloat16*)d_in[8];
  p.out = (__nv_bfloat16*)d_out;
  if (coresident) {
    fused_kernel<0><<<NCTA, NTHREADS, SMEM_BYTES>>>(p, tmX, tmW, tmWo, tmQ, tmXh, tmWh);
  } else {
    fused_kernel<0><<<4, NTHREADS, SMEM_BYTES>>>(p, tmX, tmW, tmWo, tmQ, tmXh, tmWh);
    fused_kernel<1><<<NCTA, NTHREADS, SMEM_BYTES>>>(p, tmX, tmW, tmWo, tmQ, tmXh, tmWh);
    fused_kernel<2><<<NCTA, NTHREADS, SMEM_BYTES>>>(p, tmX, tmW, tmWo, tmQ, tmXh, tmWh);
  }
}
```

```cpp
#include <cuda_runtime.h>
#include <cuda.h>
#include <cuda_bf16.h>
#include <stdint.h>

namespace {

constexpr int SEQ = 2048;
constexpr int DM = 1024;
constexpr int NCTA = 132;
constexpr int NTHREADS = 384;

constexpr int STG1A = 32768;
constexpr int NS1A = 3;
constexpr int STG1B = 12288;
constexpr int NS1B = 5;
constexpr int OFF_1B = NS1A * STG1A;
constexpr int STG2 = 32768;
constexpr int NS2 = 5;
constexpr int STGH = 73728;
constexpr int OFF_VP = 0;
constexpr int OFF_OP = 1 * STG2;
constexpr int OFF_Q = 3 * STG2;
constexpr int T_A4 = 0, T_TW = 16384, T_B2 = 24576, T_A1 = 28672, T_END = 32768;
constexpr int OFF_U = 163840;
constexpr int OFF_H = OFF_U + 32768;
constexpr int OFF_T = OFF_U - T_END;
constexpr int OFF_LAND = 4 * STG2;
constexpr int OFF_BAR = OFF_H + 32768;
constexpr int OFF_SC = OFF_BAR + 512;
constexpr int OFF_L0 = -2048;
constexpr int SMEM_BYTES = 2048 + OFF_BAR + 1024;
static_assert(OFF_T + T_A1 == OFF_1B + NS1B * STG1B && OFF_T + T_TW == OFF_1B + 4 * STG1B && OFF_LAND == OFF_T + T_A4, "layout");
static_assert(3 * STGH <= OFF_BAR && SMEM_BYTES <= 232448, "smem");

constexpr int BAR_FULLA = 0;
constexpr int BAR_EMPTYA = 3;
constexpr int BAR_FULLB = 6;
constexpr int BAR_EMPTYB = 11;
constexpr int BAR_FULL2 = 16;
constexpr int BAR_EMPTY2 = 21;
constexpr int BAR_T = 26;
constexpr int BAR_UH = 27;
constexpr int BAR_LFREE = 28;
constexpr int BAR_LAND = 29;
constexpr int BAR_U = 30;
constexpr int BAR_Q = 31;
constexpr int BAR_STG = 32;
constexpr int BAR_DEAD = 33;
constexpr int BAR_X = 35;
constexpr int BAR_REL = 36;

constexpr int NB_G1DONE = 1;
constexpr int NB_OREADY = 2;
constexpr int NB_WG = 4;
constexpr int NB_HELP3 = 6;
constexpr int NB_FIRST = 7;
constexpr int NB_LEAD = 8;

#define PACE 390u
#define PF0 20
#define PEEL 1
#define IDLEW 1
#define LA0 3
#define LA1 4
#define STAG 12
#define LAST 0
#define FINE 40
#define S1FIRST 0
#define REG_MATH 224
#define REG_HELP 56
constexpr int SPIN_LIMIT = 1 << 20;

__device__ __align__(1024) __nv_bfloat16 g_o[SEQ * DM];
__device__ uint32_t g_flag_o[256];
__device__ uint32_t g_flag_h[4];
__device__ uint4 g_halo[128 * 128];
__device__ __align__(128) const uint32_t g_tab[T_END / 4] = {
0x3c003c00,0x3bf13bff,0,0xafd6a648,0x3c003c00,0x3b993bce,0,0xb505b303,0x3c003c00,0x3af63b50,0,0xb7e3b67c,
0x3c003c00,0x3a0f3a8a,0,0xb93ab89b,0x3bc33bfe,0x3b773bfa,0xb3c6aa48,0xb5c2acb5,0x3a6d3b3b,0x389b3a4f,0xb8c4b6d7,0xba8ab8ec,
0x381d395f,0x26483505,0xbaddb9ed,0xbbffbb99,0x30b23564,0xb848b444,0xbbeabb88,0xbac2bbb6,0x3b0e3bf6,0x3a8a3bf1,0xb78bae46,0xb89bafd6,
0x34a53913,0xa6483732,0xbba8ba2f,0xbbffbb25,0xb78bae46,0xbac2b7e3,0xbb0ebbf6,0xb848baf6,0xbba8ba2f,0xbb50bbfa,0xb4a5b913,0x367cacb5,
0x39ed3bea,0x393a3be2,0xb95fb0b2,0xba0fb179,0xb56433c6,0xb8ec2648,0xbb88bbc3,0xba4fbbff,0xbbfeba6d,0xbb25bbce,0xaa48b8c4,0x3732b303,
0xb6d7badd,0x3444b67c,0x3b3b381d,0x3bb63b50,0x38723bd9,0x37323bce,0xbaa7b23e,0xbb25b303,0xbaa7b23e,0xbbb6b67c,0xb872bbd9,0xb444bb50,
0xb872bbd9,0xacb5ba8a,0x3aa7323e,0x3bfa389b,0x3aa7323e,0x3bf139cb,0x38723bd9,0xafd63984,0x35643bc3,0x33033bb6,0xbb88b3c6,0xbbceb444,
0xbbfeb8c4,0xbb77ba0f,0x2a48ba6d,0x35c2b93a,0x36d7b81d,0x3a8aafd6,0x3b3b3add,0x389b3bf1,0x395f3bea,0x26483b25,0xb9ed30b2,0xbbffb732,
0x2e463ba8,0xa6483b99,0xbbf6b4a5,0xbbffb505,0xba2fbb0e,0xb848bbb6,0x3913b78b,0x3ac2b444,0x3bf634a5,0x3b50393a,0x2e463ba8,0xb67c3a0f,
0xb913378b,0xbbe2afd6,0xba2fbb0e,0xb179bbf1,0xb0b23b88,0xb4443b77,0xbbeab564,0xbbb6b5c2,0xb3c6bbfe,0x2cb5bbe2,0x3bc3aa48,0x3bfa3179,
0x38c43b3b,0x2fd63bff,0xba6d36d7,0xbbf12648,0xbaddb95f,0xb505bbce,0x381db9ed,0x3b99b303,0xb61f3b64,0xb7e33b50,0xbb64b61f,0xbaf6b67c,
0x361fbb64,0x393aba8a,0x3b64361f,0x3a0f389b,0xb61f3b64,0xba4f3984,0xbb64b61f,0xb8ecb9cb,0x361fbb64,0x3b25b848,0x3b64361f,0x37323ac2,
0xb8c43b3b,0xb9843b25,0xba6db6d7,0xb9cbb732,0x3addb95f,0x3bceb7e3,0x381d39ed,0x33033af6,0xbbea3564,0xbb77acb5,0xb0b2bb88,0x35c2bbfa,
0x3bc32a48,0x389b38ec,0xb3c63bfe,0xba8a3a4f,0xba2f3b0e,0xbac23af6,0xb913b78b,0xb848b7e3,0x3bf6b4a5,0x3b50acb5,0xae463ba8,0xb67c3bfa,
0xb913b78b,0xb179ba4f,0x3a2fbb0e,0x3be2b8ec,0xae463ba8,0xb9cb3b99,0xbbf634a5,0xb984b505,0xbb3b3add,0xbb993ac2,0xb6d7b81d,0xb505b848,
0x39ed30b2,0x37e335c2,0xb95f3bea,0xbaf63b77,0x3564bbc3,0x3a0fbbe2,0x3b88b3c6,0x393a3179,0xbbfe38c4,0xba4f2648,0xaa48ba6d,0x38ecbbff,
0xbbd93aa7,0xbbfa3a8a,0xb23eb872,0xacb5b89b,0x323e3872,0xafd639cb,0xbbd93aa7,0xbbf13984,0x3bd9baa7,0x3b99b848,0x323e3872,0xb5053ac2,
0xb23eb872,0x37e3bb77,0x3bd9baa7,0x3af6b5c2,0xbbfe3a6d,0xbbe23a4f,0x2a48b8c4,0x3179b8ec,0xb6d73add,0xb9843b99,0xbb3b381d,0xb9cb3505,
0x395fb0b2,0x33033444,0xb9ed3bea,0xbbce3bb6,0x3b88bbc3,0x3b77b93a,0x356433c6,0xb5c23a0f,0xbba83a2f,0xbb503a0f,0x34a5b913,0x367cb93a,
0xbb0e3bf6,0xbbe23bf1,0xb78b2e46,0xb179afd6,0xb4a53913,0xb9cb3b25,0xbba83a2f,0xb9843732,0x378bae46,0xb30337e3,0xbb0e3bf6,0xbbce3af6,
0xbadd39ed,0xba4f39cb,0x381db95f,0x38ecb984,0xbbea3b88,0xbb253ac2,0x30b2b564,0x3732b848,0xbbc33bfe,0xbbb63b77,0xb3c62a48,0x3444b5c2,
0xba6d3b3b,0xbbfa3be2,0xb8c436d7,0x2cb5b179,0xb9a839a8,0xb8ec3984,0x39a8b9a8,0x3a4fb9cb,0xb9a839a8,0xb7323848,0x39a8b9a8,0x3b25bac2,
0xb9a839a8,0xb44435c2,0x39a8b9a8,0x3bb6bb77,0xb9a839a8,0xacb53179,0x39a8b9a8,0x3bfabbe2,0xb81d395f,0xb67c393a,0x3addb9ed,0x3b50ba0f,
0xb0b23564,0x31792fd6,0x3beabb88,0x3be2bbf1,0x33c6aa48,0x3984b732,0x3bc3bbfe,0x39cbbb25,0x38c4b6d7,0x3bcebaf6,0x3a6dbb3b,0x3303b7e3,
0xb4a53913,0xb17938ec,0x3ba8ba2f,0x3be2ba4f,0x378bae46,0x39cbb505,0x3b0ebbf6,0x3984bb99,0x3ba8ba2f,0x3bcebbb6,0x34a5b913,0xb303b444,
0x3b0ebbf6,0x35c2ba0f,0xb78b2e46,0xbb77393a,0xaa4838c4,0x2cb5389b,0x3bfeba6d,0x3bfaba8a,0x3b3bb81d,0x3bf1b984,0x36d7badd,0x2fd6b9cb,
0x39edbbea,0x3505bac2,0xb95f30b2,0xbb993848,0xb564b3c6,0xbaf635c2,0xbb883bc3,0xb7e33b77,0x323e3872,0x35053848,0x3bd9baa7,0x3b99bac2,
0x3bd9baa7,0x3af6bb77,0xb23eb872,0xb7e3b5c2,0xb23eb872,0xb93ab179,0xbbd93aa7,0xba0f3be2,0xbbd93aa7,0xb8ec3bff,0x323e3872,0x3a4fa648,
0x36d7381d,0x384837e3,0x3b3bbadd,0x3ac2baf6,0x395fbbea,0x367cbbfa,0xb9edb0b2,0xbb502cb5,0xbb8833c6,0xbbe238ec,0xb5643bc3,0x31793a4f,
0x2a483a6d,0x39843505,0x3bfeb8c4,0x39cbbb99,0x3913378b,0x39cb3732,0x3a2fbb0e,0x3984bb25,0x2e46bba8,0xb303baf6,0xbbf634a5,0xbbce37e3,
0xba2f3b0e,0xb5c23bfa,0x3913378b,0x3b772cb5,0x3bf6b4a5,0x3a8aba4f,0x2e46bba8,0xb89bb8ec,0x3a6d36d7,0x3af6367c,0x38c4bb3b,0x37e3bb50,
0xb81db9ed,0xba0fb89b,0xbadd395f,0xb93a3a8a,0x30b23b88,0x38ec39cb,0x3beab564,0x3a4fb984,0x33c6bbfe,0xb732bac2,0xbbc3aa48,0xbb253848,
0x3b64361f,0x3bb635c2,0x361fbb64,0x3444bb77,0xbb64b61f,0xbbfab179,0xb61f3b64,0xacb53be2,0x3b64361f,0x3bf1a648,0x361fbb64,0xafd6bbff,
0xbb64b61f,0xbb993303,0xb61f3b64,0x35053bce,0x3bea3564,0x3bff3505,0x30b2bb88,0x2648bb99,0xbbc32a48,0xbac23444,0x33c63bfe,0x38483bb6,
0x3a6db6d7,0x367cba0f,0xb8c4bb3b,0xbb50b93a,0xb81d39ed,0x31793bf1,0x3add395f,0x3be22fd6,0x3bf634a5,0x3bce3444,0xae46bba8,0xb303bbb6,
0xb913378b,0xb5c2393a,0x3a2f3b0e,0x3b773a0f,0xae46bba8,0xb89bbbf1,0xbbf6b4a5,0xba8a2fd6,0x3a2f3b0e,0x3bff3732,0x3913b78b,0xa648bb25,
0x3b8833c6,0x3b253303,0xb564bbc3,0xb732bbce,0xaa483a6d,0x34443b50,0x3bfe38c4,0x3bb6367c,0xbb3bbadd,0xbbfab89b,0xb6d7381d,0x2cb53a8a,
0x39edb0b2,0x2fd6b984,0xb95fbbea,0xbbf1b9cb,0x3aa7323e,0x3a0f3179,0xb872bbd9,0xb93abbe2,0x38723bd9,0x3a4f3bff,0x3aa7323e,0x38eca648,
0xbaa7b23e,0xb7323303,0x38723bd9,0x3b253bce,0xb872bbd9,0xbbb6bb50,0xbaa7b23e,0xb444367c,0x395f30b2,0x389b2fd6,0xb9edbbea,0xba8abbf1,
0x3b883bc3,0x3bff3b25,0x3564b3c6,0x2648b732,0x2a4838c4,0x38483af6,0x3bfe3a6d,0x3ac237e3,0xbb3bb81d,0xb67c2cb5,0x36d73add,0x3b503bfa,
0x378b2e46,0x35c22cb5,0xbb0ebbf6,0xbb77bbfa,0x3ba83a2f,0x3a8a38ec,0xb4a5b913,0xb89bba4f,0x3b0e3bf6,0x3bff3b99,0x378b2e46,0xa648b505,
0x34a53913,0x3ac23bb6,0x3ba83a2f,0x38483444,0x33c62a48,0x2fd62648,0xbbc3bbfe,0xbbf1bbff,0x38c436d7,0x35053303,0xba6dbb3b,0xbb99bbce,
0x3add39ed,0x37e3367c,0xb81db95f,0xbaf6bb50,0x3bea3b88,0x393a389b,0xb0b2b564,0xba0fba8a,0x3c003c00,0xbbf1bbff,0,0x2fd62648,
0x3c003c00,0xbb99bbce,0,0x35053303,0x3c003c00,0xbaf6bb50,0,0x37e3367c,0x3c003c00,0xba0fba8a,0,0x393a389b,
0x3bc33bfe,0xbb77bbfa,0xb3c6aa48,0x35c22cb5,0x3a6d3b3b,0xb89bba4f,0xb8c4b6d7,0x3a8a38ec,0x381d395f,0xa648b505,0xbaddb9ed,0x3bff3b99,
0x30b23564,0x38483444,0xbbeabb88,0x3ac23bb6,0x3b0e3bf6,0xba8abbf1,0xb78bae46,0x389b2fd6,0x34a53913,0x2648b732,0xbba8ba2f,0x3bff3b25,
0xb78bae46,0x3ac237e3,0xbb0ebbf6,0x38483af6,0xbba8ba2f,0x3b503bfa,0xb4a5b913,0xb67c2cb5,0x39ed3bea,0xb93abbe2,0xb95fb0b2,0x3a0f3179,
0xb56433c6,0x38eca648,0xbb88bbc3,0x3a4f3bff,0xbbfeba6d,0x3b253bce,0xaa48b8c4,0xb7323303,0xb6d7badd,0xb444367c,0x3b3b381d,0xbbb6bb50,
0x38723bd9,0xb732bbce,0xbaa7b23e,0x3b253303,0xbaa7b23e,0x3bb6367c,0xb872bbd9,0x34443b50,0xb872bbd9,0x2cb53a8a,0x3aa7323e,0xbbfab89b,
0x3aa7323e,0xbbf1b9cb,0x38723bd9,0x2fd6b984,0x35643bc3,0xb303bbb6,0xbb88b3c6,0x3bce3444,0xbbfeb8c4,0x3b773a0f,0x2a48ba6d,0xb5c2393a,
0x36d7b81d,0xba8a2fd6,0x3b3b3add,0xb89bbbf1,0x395f3bea,0xa648bb25,0xb9ed30b2,0x3bff3732,0x2e463ba8,0x2648bb99,0xbbf6b4a5,0x3bff3505,
0xba2fbb0e,0x38483bb6,0x3913b78b,0xbac23444,0x3bf634a5,0xbb50b93a,0x2e463ba8,0x367cba0f,0xb913378b,0x3be22fd6,0xba2fbb0e,0x31793bf1,
0xb0b23b88,0x3444bb77,0xbbeab564,0x3bb635c2,0xb3c6bbfe,0xacb53be2,0x3bc3aa48,0xbbfab179,0x38c43b3b,0xafd6bbff,0xba6d36d7,0x3bf1a648,
0xbaddb95f,0x35053bce,0x381db9ed,0xbb993303,0xb61f3b64,0x37e3bb50,0xbb64b61f,0x3af6367c,0x361fbb64,0xb93a3a8a,0x3b64361f,0xba0fb89b,
0xb61f3b64,0x3a4fb984,0xbb64b61f,0x38ec39cb,0x361fbb64,0xbb253848,0x3b64361f,0xb732bac2,0xb8c43b3b,0x3984bb25,0xba6db6d7,0x39cb3732,
0x3addb95f,0xbbce37e3,0x381d39ed,0xb303baf6,0xbbea3564,0x3b772cb5,0xb0b2bb88,0xb5c23bfa,0x3bc32a48,0xb89bb8ec,0xb3c63bfe,0x3a8aba4f,
0xba2f3b0e,0x3ac2baf6,0xb913b78b,0x384837e3,0x3bf6b4a5,0xbb502cb5,0xae463ba8,0x367cbbfa,0xb913b78b,0x31793a4f,0x3a2fbb0e,0xbbe238ec,
0xae463ba8,0x39cbbb99,0xbbf634a5,0x39843505,0xbb3b3add,0x3b99bac2,0xb6d7b81d,0x35053848,0x39ed30b2,0xb7e3b5c2,0xb95f3bea,0x3af6bb77,
0x3564bbc3,0xba0f3be2,0x3b88b3c6,0xb93ab179,0xbbfe38c4,0x3a4fa648,0xaa48ba6d,0xb8ec3bff,0xbbd93aa7,0x3bfaba8a,0xb23eb872,0x2cb5389b,
0x323e3872,0x2fd6b9cb,0xbbd93aa7,0x3bf1b984,0x3bd9baa7,0xbb993848,0x323e3872,0x3505bac2,0xb23eb872,0xb7e33b77,0x3bd9baa7,0xbaf635c2,
0xbbfe3a6d,0x3be2ba4f,0x2a48b8c4,0xb17938ec,0xb6d73add,0x3984bb99,0xbb3b381d,0x39cbb505,0x395fb0b2,0xb303b444,0xb9ed3bea,0x3bcebbb6,
0x3b88bbc3,0xbb77393a,0x356433c6,0x35c2ba0f,0xbba83a2f,0x3b50ba0f,0x34a5b913,0xb67c393a,0xbb0e3bf6,0x3be2bbf1,0xb78b2e46,0x31792fd6,
0xb4a53913,0x39cbbb25,0xbba83a2f,0x3984b732,0x378bae46,0x3303b7e3,0xbb0e3bf6,0x3bcebaf6,0xbadd39ed,0x3a4fb9cb,0x381db95f,0xb8ec3984,
0xbbea3b88,0x3b25bac2,0x30b2b564,0xb7323848,0xbbc33bfe,0x3bb6bb77,0xb3c62a48,0xb44435c2,0xba6d3b3b,0x3bfabbe2,0xb8c436d7,0xacb53179,
0xb9a839a8,0x38ecb984,0x39a8b9a8,0xba4f39cb,0xb9a839a8,0x3732b848,0x39a8b9a8,0xbb253ac2,0xb9a839a8,0x3444b5c2,0x39a8b9a8,0xbbb63b77,
0xb9a839a8,0x2cb5b179,0x39a8b9a8,0xbbfa3be2,0xb81d395f,0x367cb93a,0x3addb9ed,0xbb503a0f,0xb0b23564,0xb179afd6,0x3beabb88,0xbbe23bf1,
0x33c6aa48,0xb9843732,0x3bc3bbfe,0xb9cb3b25,0x38c4b6d7,0xbbce3af6,0x3a6dbb3b,0xb30337e3,0xb4a53913,0x3179b8ec,0x3ba8ba2f,0xbbe23a4f,
0x378bae46,0xb9cb3505,0x3b0ebbf6,0xb9843b99,0x3ba8ba2f,0xbbce3bb6,0x34a5b913,0x33033444,0x3b0ebbf6,0xb5c23a0f,0xb78b2e46,0x3b77b93a,
0xaa4838c4,0xacb5b89b,0x3bfeba6d,0xbbfa3a8a,0x3b3bb81d,0xbbf13984,0x36d7badd,0xafd639cb,0x39edbbea,0xb5053ac2,0xb95f30b2,0x3b99b848,
0xb564b3c6,0x3af6b5c2,0xbb883bc3,0x37e3bb77,0x323e3872,0xb505b848,0x3bd9baa7,0xbb993ac2,0x3bd9baa7,0xbaf63b77,0xb23eb872,0x37e335c2,
0xb23eb872,0x393a3179,0xbbd93aa7,0x3a0fbbe2,0xbbd93aa7,0x38ecbbff,0x323e3872,0xba4f2648,0x36d7381d,0xb848b7e3,0x3b3bbadd,0xbac23af6,
0x395fbbea,0xb67c3bfa,0xb9edb0b2,0x3b50acb5,0xbb8833c6,0x3be2b8ec,0xb5643bc3,0xb179ba4f,0x2a483a6d,0xb984b505,0x3bfeb8c4,0xb9cb3b99,
0x3913378b,0xb9cbb732,0x3a2fbb0e,0xb9843b25,0x2e46bba8,0x33033af6,0xbbf634a5,0x3bceb7e3,0xba2f3b0e,0x35c2bbfa,0x3913378b,0xbb77acb5,
0x3bf6b4a5,0xba8a3a4f,0x2e46bba8,0x389b38ec,0x3a6d36d7,0xbaf6b67c,0x38c4bb3b,0xb7e33b50,0xb81db9ed,0x3a0f389b,0xbadd395f,0x393aba8a,
0x30b23b88,0xb8ecb9cb,0x3beab564,0xba4f3984,0x33c6bbfe,0x37323ac2,0xbbc3aa48,0x3b25b848,0x3b64361f,0xbbb6b5c2,0x361fbb64,0xb4443b77,
0xbb64b61f,0x3bfa3179,0xb61f3b64,0x2cb5bbe2,0x3b64361f,0xbbf12648,0x361fbb64,0x2fd63bff,0xbb64b61f,0x3b99b303,0xb61f3b64,0xb505bbce,
0x3bea3564,0xbbffb505,0x30b2bb88,0xa6483b99,0xbbc32a48,0x3ac2b444,0x33c63bfe,0xb848bbb6,0x3a6db6d7,0xb67c3a0f,0xb8c4bb3b,0x3b50393a,
0xb81d39ed,0xb179bbf1,0x3add395f,0xbbe2afd6,0x3bf634a5,0xbbceb444,0xae46bba8,0x33033bb6,0xb913378b,0x35c2b93a,0x3a2f3b0e,0xbb77ba0f,
0xae46bba8,0x389b3bf1,0xbbf6b4a5,0x3a8aafd6,0x3a2f3b0e,0xbbffb732,0x3913b78b,0x26483b25,0x3b8833c6,0xbb25b303,0xb564bbc3,0x37323bce,
0xaa483a6d,0xb444bb50,0x3bfe38c4,0xbbb6b67c,0xbb3bbadd,0x3bfa389b,0xb6d7381d,0xacb5ba8a,0x39edb0b2,0xafd63984,0xb95fbbea,0x3bf139cb,
0x3aa7323e,0xba0fb179,0xb872bbd9,0x393a3be2,0x38723bd9,0xba4fbbff,0x3aa7323e,0xb8ec2648,0xbaa7b23e,0x3732b303,0x38723bd9,0xbb25bbce,
0xb872bbd9,0x3bb63b50,0xbaa7b23e,0x3444b67c,0x395f30b2,0xb89bafd6,0xb9edbbea,0x3a8a3bf1,0x3b883bc3,0xbbffbb25,0x3564b3c6,0xa6483732,
0x2a4838c4,0xb848baf6,0x3bfe3a6d,0xbac2b7e3,0xbb3bb81d,0x367cacb5,0x36d73add,0xbb50bbfa,0x378b2e46,0xb5c2acb5,0xbb0ebbf6,0x3b773bfa,
0x3ba83a2f,0xba8ab8ec,0xb4a5b913,0x389b3a4f,0x3b0e3bf6,0xbbffbb99,0x378b2e46,0x26483505,0x34a53913,0xbac2bbb6,0x3ba83a2f,0xb848b444,
0x33c62a48,0xafd6a648,0xbbc3bbfe,0x3bf13bff,0x38c436d7,0xb505b303,0xba6dbb3b,0x3b993bce,0x3add39ed,0xb7e3b67c,0xb81db95f,0x3af63b50,
0x3bea3b88,0xb93ab89b,0xb0b2b564,0x3a0f3a8a,0x3c003c00,0x38ec3984,0,0xba4fb9cb,0x3c003c00,0x37323848,0,0xbb25bac2,
0x3c003c00,0x344435c2,0,0xbbb6bb77,0x3c003c00,0x2cb53179,0,0xbbfabbe2,0xb3c6aa48,0xbb50ba0f,0xbbc3bbfe,0xb67cb93a,
0xb8c4b6d7,0xbbe2bbf1,0xba6dbb3b,0x3179afd6,0xbaddb9ed,0xb9cbbb25,0xb81db95f,0x39843732,0xbbeabb88,0xb303b7e3,0xb0b2b564,0x3bce3af6,
0xbb0ebbf6,0xb179b8ec,0x378b2e46,0x3be23a4f,0xb4a5b913,0x39cb3505,0x3ba83a2f,0x39843b99,0x378b2e46,0x3bce3bb6,0x3b0e3bf6,0xb3033444,
0x3ba83a2f,0x35c23a0f,0x34a53913,0xbb77b93a,0x395f30b2,0x3bfa3a8a,0x39ed3bea,0xacb5389b,0x3b883bc3,0x2fd639cb,0xb56433c6,0xbbf1b984,
0x2a4838c4,0xbb99b848,0xbbfeba6d,0xb505bac2,0xbb3bb81d,0xb7e3bb77,0xb6d7badd,0x3af635c2,0x38723bd9,0xb5053848,0xbaa7b23e,0xbb99bac2,
0xbaa7b23e,0xbaf6bb77,0xb872bbd9,0x37e3b5c2,0xb872bbd9,0x393ab179,0x3aa7323e,0x3a0f3be2,0x3aa7323e,0x38ec3bff,0x38723bd9,0xba4fa648,
0xbb88b3c6,0xbac2baf6,0xb564bbc3,0x3848b7e3,0x2a48ba6d,0x3b502cb5,0x3bfe38c4,0x367c3bfa,0x3b3b3add,0xb1793a4f,0xb6d7381d,0xbbe2b8ec,
0xb9ed30b2,0xb9cbbb99,0xb95fbbea,0x3984b505,0xae46bba8,0x39cbb732,0x3bf634a5,0x39843b25,0x3a2f3b0e,0xb3033af6,0xb913378b,0xbbceb7e3,
0xbbf6b4a5,0xb5c2bbfa,0xae46bba8,0x3b77acb5,0x3913b78b,0x3a8a3a4f,0x3a2f3b0e,0xb89b38ec,0x3bea3564,0x37e33b50,0xb0b23b88,0xbaf6367c,
0xbbc32a48,0xb93aba8a,0xb3c6bbfe,0x3a0fb89b,0x3a6db6d7,0x3a4f3984,0x38c43b3b,0xb8ec39cb,0xb81d39ed,0xbb25b848,0xbaddb95f,0x3732bac2,
0xb61f3b64,0xbbb635c2,0xbb64b61f,0xb444bb77,0x361fbb64,0x3bfab179,0x3b64361f,0x2cb53be2,0xb61f3b64,0xbbf1a648,0xbb64b61f,0x2fd6bbff,
0x361fbb64,0x3b993303,0x3b64361f,0xb5053bce,0xba6db6d7,0xa648bb99,0x38c4bb3b,0x3bffb505,0x381d39ed,0xb8483bb6,0xbadd395f,0xbac2b444,
0xb0b2bb88,0x3b50b93a,0x3beab564,0x367c3a0f,0xb3c63bfe,0xbbe22fd6,0xbbc3aa48,0x3179bbf1,0x3a2fbb0e,0x3bceb444,0x3913378b,0xb3033bb6,
0xbbf634a5,0xb5c2b93a,0x2e46bba8,0x3b77ba0f,0x3913378b,0xb89b3bf1,0xba2f3b0e,0xba8aafd6,0x2e46bba8,0x3bffb732,0x3bf6b4a5,0xa6483b25,
0x36d7381d,0xb7323bce,0xbb3b3add,0xbb253303,0x395fbbea,0x3bb6b67c,0x39ed30b2,0xb4443b50,0xbb8833c6,0x2cb5ba8a,0x3564bbc3,0x3bfab89b,
0x2a483a6d,0xbbf139cb,0xbbfe38c4,0xafd6b984,0xbbd93aa7,0xba0f3179,0xb23eb872,0x393abbe2,0x323e3872,0xba4f3bff,0xbbd93aa7,0xb8eca648,
0x3bd9baa7,0x37323303,0x323e3872,0xbb253bce,0xb23eb872,0x3bb6bb50,0x3bd9baa7,0x3444367c,0x2a48b8c4,0x3a8abbf1,0x3bfeba6d,0x389bafd6,
0xbb3b381d,0xa648b732,0x36d7badd,0x3bffbb25,0xb9ed3bea,0xbac237e3,0xb95f30b2,0x3848baf6,0x356433c6,0xbb503bfa,0xbb883bc3,0xb67cacb5,
0x3ba8ba2f,0x35c2acb5,0xb4a53913,0xbb773bfa,0x3b0ebbf6,0x3a8ab8ec,0x378bae46,0xb89b3a4f,0x34a5b913,0x3bffbb99,0x3ba8ba2f,0xa6483505,
0xb78b2e46,0x3ac2bbb6,0x3b0ebbf6,0x3848b444,0xb81d395f,0xbbf13bff,0xbadd39ed,0xafd62648,0xb0b23564,0xbb993bce,0xbbea3b88,0xb5053303,
0x33c6aa48,0xbaf63b50,0xbbc33bfe,0xb7e3367c,0x38c4b6d7,0xba0f3a8a,0xba6d3b3b,0xb93a389b,0xb9a839a8,0x2fd6a648,0x39a8b9a8,0x3bf1bbff,
0xb9a839a8,0x3505b303,0x39a8b9a8,0x3b99bbce,0xb9a839a8,0x37e3b67c,0x39a8b9a8,0x3af6bb50,0xb9a839a8,0x393ab89b,0x39a8b9a8,0x3a0fba8a,
0x3addb9ed,0x3b77bbfa,0x381db95f,0xb5c22cb5,0x3beabb88,0x389bba4f,0x30b2b564,0xba8a38ec,0x3bc3bbfe,0x2648b505,0xb3c62a48,0xbbff3b99,
0x3a6dbb3b,0xb8483444,0xb8c436d7,0xbac23bb6,0x34a5b913,0xb89b2fd6,0xbba83a2f,0xba8a3bf1,0xb78b2e46,0xbbff3b25,0xbb0e3bf6,0x26483732,
0xbba83a2f,0xb8483af6,0xb4a53913,0x3ac2b7e3,0xbb0e3bf6,0x367c2cb5,0x378bae46,0x3b50bbfa,0xbbfe3a6d,0xb93a3be2,0xaa4838c4,0x3a0fb179,
0xb6d73add,0x38ec2648,0x3b3bb81d,0x3a4fbbff,0x395fb0b2,0x3b25bbce,0x39edbbea,0xb732b303,0x3b88bbc3,0xb444b67c,0xb564b3c6,0xbbb63b50,
0x323e3872,0x3b25b303,0x3bd9baa7,0x3732bbce,0x3bd9baa7,0x3444bb50,0xb23eb872,0xbbb6367c,0xb23eb872,0xbbfa389b,0xbbd93aa7,0xacb53a8a,
0xbbd93aa7,0x2fd63984,0x323e3872,0x3bf1b9cb,0x3b3bbadd,0x3303bbb6,0xb6d7b81d,0xbbce3444,0xb9edb0b2,0xbb773a0f,0xb95f3bea,0x35c2393a,
0xb5643bc3,0x3a8a2fd6,0x3b88b3c6,0x389bbbf1,0x3bfeb8c4,0x2648bb25,0xaa48ba6d,0xbbff3732,0xb913b78b,0xbbff3505,0xba2f3b0e,0x26483b99,
0xae463ba8,0x3ac23444,0x3bf6b4a5,0x3848bbb6,0x3a2fbb0e,0xb67cba0f,0xb913b78b,0xbb50393a,0xbbf634a5,0xb1793bf1,0xae463ba8,0x3be2afd6,
0xb8c43b3b,0x34443b77,0x3a6d36d7,0x3bb6b5c2,0x3addb95f,0xacb5bbe2,0xb81db9ed,0xbbfa3179,0xbbea3564,0xafd63bff,0x30b23b88,0x3bf12648,
0x3bc32a48,0x3505bbce,0x33c6bbfe,0xbb99b303,0x3b64361f,0x3af6b67c,0x361fbb64,0xb7e3bb50,0xbb64b61f,0xba0f389b,0xb61f3b64,0x393a3a8a,
0x3b64361f,0x38ecb9cb,0x361fbb64,0xba4fb984,0xbb64b61f,0xb7323ac2,0xb61f3b64,0x3b253848,0x30b2bb88,0xb984bb25,0xbbeab564,0xb9cb3732,
0x33c63bfe,0x3bce37e3,0x3bc3aa48,0x3303baf6,0xb8c4bb3b,0xbb772cb5,0xba6d36d7,0x35c23bfa,0x3add395f,0x389bb8ec,0x381db9ed,0xba8aba4f,
0xbbf6b4a5,0xb84837e3,0x2e463ba8,0x3ac23af6,0x3913b78b,0xb67cbbfa,0xba2fbb0e,0xbb50acb5,0x2e463ba8,0x3be238ec,0x3bf634a5,0x3179ba4f,
0xba2fbb0e,0xb9843505,0xb913378b,0x39cb3b99,0x35643bc3,0x3b993ac2,0x3b8833c6,0x3505b848,0xbbfeb8c4,0xb7e335c2,0xaa483a6d,0x3af63b77,
0x36d7b81d,0xba0fbbe2,0xbb3bbadd,0xb93a3179,0x395f3bea,0x3a4f2648,0x39edb0b2,0xb8ecbbff,0x3aa7323e,0x2cb5b89b,0xb872bbd9,0xbbfaba8a,
0x38723bd9,0x3bf13984,0x3aa7323e,0xafd6b9cb,0xbaa7b23e,0x35053ac2,0x38723bd9,0x3b993848,0xb872bbd9,0xbaf6b5c2,0xbaa7b23e,0x37e33b77,
0xb9edbbea,0xbbe2ba4f,0xb95fb0b2,0x317938ec,0x3564b3c6,0xb984bb99,0xbb88bbc3,0xb9cbb505,0x3bfe3a6d,0x3303b444,0xaa48b8c4,0xbbcebbb6,
0x36d73add,0x3b77393a,0x3b3b381d,0xb5c2ba0f,0xb78bae46,0x367c393a,0x3b0e3bf6,0x3b503a0f,0xbba8ba2f,0xb1792fd6,0x34a53913,0x3be23bf1,
0xbb0ebbf6,0xb984b732,0xb78bae46,0x39cb3b25,0xb4a5b913,0xbbcebaf6,0xbba8ba2f,0x330337e3,0x3bc33bfe,0x3a4f39cb,0x33c62a48,0xb8ecb984,
0x3a6d3b3b,0x3b253ac2,0x38c436d7,0xb732b848,0x381d395f,0x3bb63b77,0x3add39ed,0xb444b5c2,0x30b23564,0x3bfa3be2,0x3bea3b88,0xacb5b179,
0x3c003c00,0xb8ecb984,0,0x3a4f39cb,0x3c003c00,0xb732b848,0,0x3b253ac2,0x3c003c00,0xb444b5c2,0,0x3bb63b77,
0x3c003c00,0xacb5b179,0,0x3bfa3be2,0xb3c6aa48,0x3b503a0f,0xbbc3bbfe,0x367c393a,0xb8c4b6d7,0x3be23bf1,0xba6dbb3b,0xb1792fd6,
0xbaddb9ed,0x39cb3b25,0xb81db95f,0xb984b732,0xbbeabb88,0x330337e3,0xb0b2b564,0xbbcebaf6,0xbb0ebbf6,0x317938ec,0x378b2e46,0xbbe2ba4f,
0xb4a5b913,0xb9cbb505,0x3ba83a2f,0xb984bb99,0x378b2e46,0xbbcebbb6,0x3b0e3bf6,0x3303b444,0x3ba83a2f,0xb5c2ba0f,0x34a53913,0x3b77393a,
0x395f30b2,0xbbfaba8a,0x39ed3bea,0x2cb5b89b,0x3b883bc3,0xafd6b9cb,0xb56433c6,0x3bf13984,0x2a4838c4,0x3b993848,0xbbfeba6d,0x35053ac2,
0xbb3bb81d,0x37e33b77,0xb6d7badd,0xbaf6b5c2,0x38723bd9,0x3505b848,0xbaa7b23e,0x3b993ac2,0xbaa7b23e,0x3af63b77,0xb872bbd9,0xb7e335c2,
0xb872bbd9,0xb93a3179,0x3aa7323e,0xba0fbbe2,0x3aa7323e,0xb8ecbbff,0x38723bd9,0x3a4f2648,0xbb88b3c6,0x3ac23af6,0xb564bbc3,0xb84837e3,
0x2a48ba6d,0xbb50acb5,0x3bfe38c4,0xb67cbbfa,0x3b3b3add,0x3179ba4f,0xb6d7381d,0x3be238ec,0xb9ed30b2,0x39cb3b99,0xb95fbbea,0xb9843505,
0xae46bba8,0xb9cb3732,0x3bf634a5,0xb984bb25,0x3a2f3b0e,0x3303baf6,0xb913378b,0x3bce37e3,0xbbf6b4a5,0x35c23bfa,0xae46bba8,0xbb772cb5,
0x3913b78b,0xba8aba4f,0x3a2f3b0e,0x389bb8ec,0x3bea3564,0xb7e3bb50,0xb0b23b88,0x3af6b67c,0xbbc32a48,0x393a3a8a,0xb3c6bbfe,0xba0f389b,
0x3a6db6d7,0xba4fb984,0x38c43b3b,0x38ecb9cb,0xb81d39ed,0x3b253848,0xbaddb95f,0xb7323ac2,0xb61f3b64,0x3bb6b5c2,0xbb64b61f,0x34443b77,
0x361fbb64,0xbbfa3179,0x3b64361f,0xacb5bbe2,0xb61f3b64,0x3bf12648,0xbb64b61f,0xafd63bff,0x361fbb64,0xbb99b303,0x3b64361f,0x3505bbce,
0xba6db6d7,0x26483b99,0x38c4bb3b,0xbbff3505,0x381d39ed,0x3848bbb6,0xbadd395f,0x3ac23444,0xb0b2bb88,0xbb50393a,0x3beab564,0xb67cba0f,
0xb3c63bfe,0x3be2afd6,0xbbc3aa48,0xb1793bf1,0x3a2fbb0e,0xbbce3444,0x3913378b,0x3303bbb6,0xbbf634a5,0x35c2393a,0x2e46bba8,0xbb773a0f,
0x3913378b,0x389bbbf1,0xba2f3b0e,0x3a8a2fd6,0x2e46bba8,0xbbff3732,0x3bf6b4a5,0x2648bb25,0x36d7381d,0x3732bbce,0xbb3b3add,0x3b25b303,
0x395fbbea,0xbbb6367c,0x39ed30b2,0x3444bb50,0xbb8833c6,0xacb53a8a,0x3564bbc3,0xbbfa389b,0x2a483a6d,0x3bf1b9cb,0xbbfe38c4,0x2fd63984,
0xbbd93aa7,0x3a0fb179,0xb23eb872,0xb93a3be2,0x323e3872,0x3a4fbbff,0xbbd93aa7,0x38ec2648,0x3bd9baa7,0xb732b303,0x323e3872,0x3b25bbce,
0xb23eb872,0xbbb63b50,0x3bd9baa7,0xb444b67c,0x2a48b8c4,0xba8a3bf1,0x3bfeba6d,0xb89b2fd6,0xbb3b381d,0x26483732,0x36d7badd,0xbbff3b25,
0xb9ed3bea,0x3ac2b7e3,0xb95f30b2,0xb8483af6,0x356433c6,0x3b50bbfa,0xbb883bc3,0x367c2cb5,0x3ba8ba2f,0xb5c22cb5,0xb4a53913,0x3b77bbfa,
0x3b0ebbf6,0xba8a38ec,0x378bae46,0x389bba4f,0x34a5b913,0xbbff3b99,0x3ba8ba2f,0x2648b505,0xb78b2e46,0xbac23bb6,0x3b0ebbf6,0xb8483444,
0xb81d395f,0x3bf1bbff,0xbadd39ed,0x2fd6a648,0xb0b23564,0x3b99bbce,0xbbea3b88,0x3505b303,0x33c6aa48,0x3af6bb50,0xbbc33bfe,0x37e3b67c,
0x38c4b6d7,0x3a0fba8a,0xba6d3b3b,0x393ab89b,0xb9a839a8,0xafd62648,0x39a8b9a8,0xbbf13bff,0xb9a839a8,0xb5053303,0x39a8b9a8,0xbb993bce,
0xb9a839a8,0xb7e3367c,0x39a8b9a8,0xbaf63b50,0xb9a839a8,0xb93a389b,0x39a8b9a8,0xba0f3a8a,0x3addb9ed,0xbb773bfa,0x381db95f,0x35c2acb5,
0x3beabb88,0xb89b3a4f,0x30b2b564,0x3a8ab8ec,0x3bc3bbfe,0xa6483505,0xb3c62a48,0x3bffbb99,0x3a6dbb3b,0x3848b444,0xb8c436d7,0x3ac2bbb6,
0x34a5b913,0x389bafd6,0xbba83a2f,0x3a8abbf1,0xb78b2e46,0x3bffbb25,0xbb0e3bf6,0xa648b732,0xbba83a2f,0x3848baf6,0xb4a53913,0xbac237e3,
0xbb0e3bf6,0xb67cacb5,0x378bae46,0xbb503bfa,0xbbfe3a6d,0x393abbe2,0xaa4838c4,0xba0f3179,0xb6d73add,0xb8eca648,0x3b3bb81d,0xba4f3bff,
0x395fb0b2,0xbb253bce,0x39edbbea,0x37323303,0x3b88bbc3,0x3444367c,0xb564b3c6,0x3bb6bb50,0x323e3872,0xbb253303,0x3bd9baa7,0xb7323bce,
0x3bd9baa7,0xb4443b50,0xb23eb872,0x3bb6b67c,0xb23eb872,0x3bfab89b,0xbbd93aa7,0x2cb5ba8a,0xbbd93aa7,0xafd6b984,0x323e3872,0xbbf139cb,
0x3b3bbadd,0xb3033bb6,0xb6d7b81d,0x3bceb444,0xb9edb0b2,0x3b77ba0f,0xb95f3bea,0xb5c2b93a,0xb5643bc3,0xba8aafd6,0x3b88b3c6,0xb89b3bf1,
0x3bfeb8c4,0xa6483b25,0xaa48ba6d,0x3bffb732,0xb913b78b,0x3bffb505,0xba2f3b0e,0xa648bb99,0xae463ba8,0xbac2b444,0x3bf6b4a5,0xb8483bb6,
0x3a2fbb0e,0x367c3a0f,0xb913b78b,0x3b50b93a,0xbbf634a5,0x3179bbf1,0xae463ba8,0xbbe22fd6,0xb8c43b3b,0xb444bb77,0x3a6d36d7,0xbbb635c2,
0x3addb95f,0x2cb53be2,0xb81db9ed,0x3bfab179,0xbbea3564,0x2fd6bbff,0x30b23b88,0xbbf1a648,0x3bc32a48,0xb5053bce,0x33c6bbfe,0x3b993303,
0x3b64361f,0xbaf6367c,0x361fbb64,0x37e33b50,0xbb64b61f,0x3a0fb89b,0xb61f3b64,0xb93aba8a,0x3b64361f,0xb8ec39cb,0x361fbb64,0x3a4f3984,
0xbb64b61f,0x3732bac2,0xb61f3b64,0xbb25b848,0x30b2bb88,0x39843b25,0xbbeab564,0x39cbb732,0x33c63bfe,0xbbceb7e3,0x3bc3aa48,0xb3033af6,
0xb8c4bb3b,0x3b77acb5,0xba6d36d7,0xb5c2bbfa,0x3add395f,0xb89b38ec,0x381db9ed,0x3a8a3a4f,0xbbf6b4a5,0x3848b7e3,0x2e463ba8,0xbac2baf6,
0x3913b78b,0x367c3bfa,0xba2fbb0e,0x3b502cb5,0x2e463ba8,0xbbe2b8ec,0x3bf634a5,0xb1793a4f,0xba2fbb0e,0x3984b505,0xb913378b,0xb9cbbb99,
0x35643bc3,0xbb99bac2,0x3b8833c6,0xb5053848,0xbbfeb8c4,0x37e3b5c2,0xaa483a6d,0xbaf6bb77,0x36d7b81d,0x3a0f3be2,0xbb3bbadd,0x393ab179,
0x395f3bea,0xba4fa648,0x39edb0b2,0x38ec3bff,0x3aa7323e,0xacb5389b,0xb872bbd9,0x3bfa3a8a,0x38723bd9,0xbbf1b984,0x3aa7323e,0x2fd639cb,
0xbaa7b23e,0xb505bac2,0x38723bd9,0xbb99b848,0xb872bbd9,0x3af635c2,0xbaa7b23e,0xb7e3bb77,0xb9edbbea,0x3be23a4f,0xb95fb0b2,0xb179b8ec,
0x3564b3c6,0x39843b99,0xbb88bbc3,0x39cb3505,0x3bfe3a6d,0xb3033444,0xaa48b8c4,0x3bce3bb6,0x36d73add,0xbb77b93a,0x3b3b381d,0x35c23a0f,
0xb78bae46,0xb67cb93a,0x3b0e3bf6,0xbb50ba0f,0xbba8ba2f,0x3179afd6,0x34a53913,0xbbe2bbf1,0xbb0ebbf6,0x39843732,0xb78bae46,0xb9cbbb25,
0xb4a5b913,0x3bce3af6,0xbba8ba2f,0xb303b7e3,0x3bc33bfe,0xba4fb9cb,0x33c62a48,0x38ec3984,0x3a6d3b3b,0xbb25bac2,0x38c436d7,0x37323848,
0x381d395f,0xbbb6bb77,0x3add39ed,0x344435c2,0x30b23564,0xbbfabbe2,0x3bea3b88,0x2cb53179,0x3c003c00,0xafd6a648,0,0xbbf1bbff,
0x3c003c00,0xb505b303,0,0xbb99bbce,0x3c003c00,0xb7e3b67c,0,0xbaf6bb50,0x3c003c00,0xb93ab89b,0,0xba0fba8a,
0xbbc3bbfe,0x35c22cb5,0x33c62a48,0x3b773bfa,0xba6dbb3b,0x3a8a38ec,0x38c436d7,0x389b3a4f,0xb81db95f,0x3bff3b99,0x3add39ed,0x26483505,
0xb0b2b564,0x3ac23bb6,0x3bea3b88,0xb848b444,0x3b0e3bf6,0xb89bafd6,0xb78bae46,0xba8abbf1,0x34a53913,0xbbffbb25,0xbba8ba2f,0x2648b732,
0xb78bae46,0xb848baf6,0xbb0ebbf6,0x3ac237e3,0xbba8ba2f,0x367cacb5,0xb4a5b913,0x3b503bfa,0xb9edbbea,0x3a0f3179,0x395f30b2,0x393a3be2,
0x3564b3c6,0x3a4f3bff,0x3b883bc3,0xb8ec2648,0x3bfe3a6d,0xb7323303,0x2a4838c4,0xbb25bbce,0x36d73add,0xbbb6bb50,0xbb3bb81d,0x3444b67c,
0x38723bd9,0xbb25b303,0xbaa7b23e,0xb732bbce,0xbaa7b23e,0xb444bb50,0xb872bbd9,0x3bb6367c,0xb872bbd9,0x3bfa389b,0x3aa7323e,0x2cb53a8a,
0x3aa7323e,0xafd63984,0x38723bd9,0xbbf1b9cb,0xb564bbc3,0x3bce3444,0x3b8833c6,0x33033bb6,0x3bfe38c4,0xb5c2393a,0xaa483a6d,0xbb77ba0f,
0xb6d7381d,0xb89bbbf1,0xbb3bbadd,0x3a8aafd6,0xb95fbbea,0x3bff3732,0x39edb0b2,0x26483b25,0x2e463ba8,0xbbffb505,0xbbf6b4a5,0x2648bb99,
0xba2fbb0e,0x3ac2b444,0x3913b78b,0x38483bb6,0x3bf634a5,0xb67c3a0f,0x2e463ba8,0xbb50b93a,0xb913378b,0xb179bbf1,0xba2fbb0e,0x3be22fd6,
0x30b2bb88,0x3bb635c2,0x3bea3564,0xb4443b77,0x33c63bfe,0xbbfab179,0xbbc32a48,0x2cb5bbe2,0xb8c4bb3b,0x3bf1a648,0x3a6db6d7,0x2fd63bff,
0x3add395f,0xbb993303,0xb81d39ed,0xb505bbce,0xb61f3b64,0xbaf6b67c,0xbb64b61f,0x37e3bb50,0x361fbb64,0x3a0f389b,0x3b64361f,0xb93a3a8a,
0xb61f3b64,0xb8ecb9cb,0xbb64b61f,0x3a4fb984,0x361fbb64,0x37323ac2,0x3b64361f,0xbb253848,0x38c4bb3b,0x39cb3732,0x3a6d36d7,0xb9843b25,
0xbadd395f,0xb303baf6,0xb81db9ed,0x3bceb7e3,0x3beab564,0xb5c23bfa,0x30b23b88,0xbb77acb5,0xbbc3aa48,0x3a8aba4f,0x33c6bbfe,0x389b38ec,
0xba2f3b0e,0xb848b7e3,0xb913b78b,0x3ac2baf6,0x3bf6b4a5,0xb67c3bfa,0xae463ba8,0xbb502cb5,0xb913b78b,0x3be2b8ec,0x3a2fbb0e,0x31793a4f,
0xae463ba8,0xb984b505,0xbbf634a5,0x39cbbb99,0x3b3bbadd,0x35053848,0x36d7381d,0xbb993ac2,0xb9edb0b2,0x3af6bb77,0x395fbbea,0x37e335c2,
0xb5643bc3,0xb93ab179,0xbb8833c6,0x3a0fbbe2,0x3bfeb8c4,0xb8ec3bff,0x2a483a6d,0xba4f2648,0xbbd93aa7,0xacb5b89b,0xb23eb872,0x3bfaba8a,
0x323e3872,0xbbf13984,0xbbd93aa7,0x2fd6b9cb,0x3bd9baa7,0xb5053ac2,0x323e3872,0xbb993848,0xb23eb872,0x3af6b5c2,0x3bd9baa7,0xb7e33b77,
0x3bfeba6d,0xb17938ec,0xaa4838c4,0xbbe23a4f,0x36d7badd,0x39cbb505,0x3b3bb81d,0xb9843b99,0xb95f30b2,0x3bcebbb6,0x39edbbea,0x33033444,
0xbb883bc3,0x35c2ba0f,0xb564b3c6,0x3b77b93a,0xbba83a2f,0x367cb93a,0x34a5b913,0x3b50ba0f,0xbb0e3bf6,0xb179afd6,0xb78b2e46,0x3be2bbf1,
0xb4a53913,0xb9843732,0xbba83a2f,0x39cbbb25,0x378bae46,0xbbce3af6,0xbb0e3bf6,0x3303b7e3,0x3addb9ed,0xb8ec3984,0xb81d395f,0xba4f39cb,
0x3beabb88,0xb7323848,0xb0b23564,0xbb253ac2,0x3bc3bbfe,0xb44435c2,0x33c6aa48,0xbbb63b77,0x3a6dbb3b,0xacb53179,0x38c4b6d7,0xbbfa3be2,
0xb9a839a8,0x3a4fb9cb,0x39a8b9a8,0x38ecb984,0xb9a839a8,0x3b25bac2,0x39a8b9a8,0x3732b848,0xb9a839a8,0x3bb6bb77,0x39a8b9a8,0x3444b5c2,
0xb9a839a8,0x3bfabbe2,0x39a8b9a8,0x2cb5b179,0x381db95f,0xbb503a0f,0xbadd39ed,0xb67c393a,0x30b2b564,0xbbe23bf1,0xbbea3b88,0x31792fd6,
0xb3c62a48,0xb9cb3b25,0xbbc33bfe,0x3984b732,0xb8c436d7,0xb30337e3,0xba6d3b3b,0x3bcebaf6,0xb4a53913,0x3be2ba4f,0x3ba8ba2f,0x3179b8ec,
0x378bae46,0x3984bb99,0x3b0ebbf6,0xb9cb3505,0x3ba8ba2f,0xb303b444,0x34a5b913,0xbbce3bb6,0x3b0ebbf6,0xbb77393a,0xb78b2e46,0xb5c23a0f,
0x2a48b8c4,0xbbfa3a8a,0xbbfe3a6d,0x2cb5389b,0xbb3b381d,0xafd639cb,0xb6d73add,0x3bf1b984,0xb9ed3bea,0x3b99b848,0x395fb0b2,0x3505bac2,
0x356433c6,0x37e3bb77,0x3b88bbc3,0xbaf635c2,0x323e3872,0x3b99bac2,0x3bd9baa7,0xb505b848,0x3bd9baa7,0xb7e3b5c2,0xb23eb872,0xbaf63b77,
0xb23eb872,0xba0f3be2,0xbbd93aa7,0x393a3179,0xbbd93aa7,0x3a4fa648,0x323e3872,0x38ecbbff,0xb6d7b81d,0xbac23af6,0xbb3b3add,0x384837e3,
0xb95f3bea,0x3b50acb5,0x39ed30b2,0x367cbbfa,0x3b88b3c6,0xb179ba4f,0x3564bbc3,0xbbe238ec,0xaa48ba6d,0xb9cb3b99,0xbbfe38c4,0x39843505,
0x3913378b,0x3984bb25,0x3a2fbb0e,0xb9cbb732,0x2e46bba8,0xbbce37e3,0xbbf634a5,0x33033af6,0xba2f3b0e,0x3b772cb5,0x3913378b,0x35c2bbfa,
0x3bf6b4a5,0xb89bb8ec,0x2e46bba8,0xba8a3a4f,0xba6db6d7,0xb7e33b50,0xb8c43b3b,0x3af6367c,0x381d39ed,0x393aba8a,0x3addb95f,0xba0fb89b,
0xb0b2bb88,0xba4f3984,0xbbea3564,0x38ec39cb,0xb3c63bfe,0x3b25b848,0x3bc32a48,0xb732bac2,0x3b64361f,0x3444bb77,0x361fbb64,0xbbb6b5c2,
0xbb64b61f,0xacb53be2,0xb61f3b64,0x3bfa3179,0x3b64361f,0xafd6bbff,0x361fbb64,0xbbf12648,0xbb64b61f,0x35053bce,0xb61f3b64,0x3b99b303,
0xbbeab564,0xa6483b99,0xb0b23b88,0x3bff3505,0x3bc3aa48,0xb848bbb6,0xb3c6bbfe,0xbac23444,0xba6d36d7,0x3b50393a,0x38c43b3b,0x367cba0f,
0x381db9ed,0xbbe2afd6,0xbaddb95f,0x31793bf1,0x3bf634a5,0xb303bbb6,0xae46bba8,0xbbceb444,0xb913378b,0x3b773a0f,0x3a2f3b0e,0x35c2b93a,
0xae46bba8,0xba8a2fd6,0xbbf6b4a5,0x389b3bf1,0x3a2f3b0e,0xa648bb25,0x3913b78b,0xbbffb732,0xbb88b3c6,0x37323bce,0x35643bc3,0x3b253303,
0x2a48ba6d,0xbbb6b67c,0xbbfeb8c4,0x34443b50,0x3b3b3add,0xacb5ba8a,0x36d7b81d,0xbbfab89b,0xb9ed30b2,0x3bf139cb,0x395f3bea,0x2fd6b984,
0x3aa7323e,0xb93abbe2,0xb872bbd9,0xba0fb179,0x38723bd9,0x38eca648,0x3aa7323e,0xba4fbbff,0xbaa7b23e,0x3b253bce,0x38723bd9,0x3732b303,
0xb872bbd9,0xb444367c,0xbaa7b23e,0x3bb63b50,0xb95fb0b2,0x3a8a3bf1,0x39ed3bea,0x389b2fd6,0xbb88bbc3,0xa6483732,0xb56433c6,0x3bff3b25,
0xaa48b8c4,0xbac2b7e3,0xbbfeba6d,0x38483af6,0x3b3b381d,0xbb50bbfa,0xb6d7badd,0xb67c2cb5,0x378b2e46,0xbb77bbfa,0xbb0ebbf6,0xb5c2acb5,
0x3ba83a2f,0xb89bba4f,0xb4a5b913,0xba8ab8ec,0x3b0e3bf6,0xa648b505,0x378b2e46,0xbbffbb99,0x34a53913,0x38483444,0x3ba83a2f,0xbac2bbb6,
0xb3c6aa48,0x3bf13bff,0x3bc33bfe,0x2fd62648,0xb8c4b6d7,0x3b993bce,0x3a6d3b3b,0x35053303,0xbaddb9ed,0x3af63b50,0x381d395f,0x37e3367c,
0xbbeabb88,0x3a0f3a8a,0x30b23564,0x393a389b,0x3c003c00,0x2fd62648,0,0x3bf13bff,0x3c003c00,0x35053303,0,0x3b993bce,
0x3c003c00,0x37e3367c,0,0x3af63b50,0x3c003c00,0x393a389b,0,0x3a0f3a8a,0xbbc3bbfe,0xb5c2acb5,0x33c62a48,0xbb77bbfa,
0xba6dbb3b,0xba8ab8ec,0x38c436d7,0xb89bba4f,0xb81db95f,0xbbffbb99,0x3add39ed,0xa648b505,0xb0b2b564,0xbac2bbb6,0x3bea3b88,0x38483444,
0x3b0e3bf6,0x389b2fd6,0xb78bae46,0x3a8a3bf1,0x34a53913,0x3bff3b25,0xbba8ba2f,0xa6483732,0xb78bae46,0x38483af6,0xbb0ebbf6,0xbac2b7e3,
0xbba8ba2f,0xb67c2cb5,0xb4a5b913,0xbb50bbfa,0xb9edbbea,0xba0fb179,0x395f30b2,0xb93abbe2,0x3564b3c6,0xba4fbbff,0x3b883bc3,0x38eca648,
0x3bfe3a6d,0x3732b303,0x2a4838c4,0x3b253bce,0x36d73add,0x3bb63b50,0xbb3bb81d,0xb444367c,0x38723bd9,0x3b253303,0xbaa7b23e,0x37323bce,
0xbaa7b23e,0x34443b50,0xb872bbd9,0xbbb6b67c,0xb872bbd9,0xbbfab89b,0x3aa7323e,0xacb5ba8a,0x3aa7323e,0x2fd6b984,0x38723bd9,0x3bf139cb,
0xb564bbc3,0xbbceb444,0x3b8833c6,0xb303bbb6,0x3bfe38c4,0x35c2b93a,0xaa483a6d,0x3b773a0f,0xb6d7381d,0x389b3bf1,0xbb3bbadd,0xba8a2fd6,
0xb95fbbea,0xbbffb732,0x39edb0b2,0xa648bb25,0x2e463ba8,0x3bff3505,0xbbf6b4a5,0xa6483b99,0xba2fbb0e,0xbac23444,0x3913b78b,0xb848bbb6,
0x3bf634a5,0x367cba0f,0x2e463ba8,0x3b50393a,0xb913378b,0x31793bf1,0xba2fbb0e,0xbbe2afd6,0x30b2bb88,0xbbb6b5c2,0x3bea3564,0x3444bb77,
0x33c63bfe,0x3bfa3179,0xbbc32a48,0xacb53be2,0xb8c4bb3b,0xbbf12648,0x3a6db6d7,0xafd6bbff,0x3add395f,0x3b99b303,0xb81d39ed,0x35053bce,
0xb61f3b64,0x3af6367c,0xbb64b61f,0xb7e33b50,0x361fbb64,0xba0fb89b,0x3b64361f,0x393aba8a,0xb61f3b64,0x38ec39cb,0xbb64b61f,0xba4f3984,
0x361fbb64,0xb732bac2,0x3b64361f,0x3b25b848,0x38c4bb3b,0xb9cbb732,0x3a6d36d7,0x3984bb25,0xbadd395f,0x33033af6,0xb81db9ed,0xbbce37e3,
0x3beab564,0x35c2bbfa,0x30b23b88,0x3b772cb5,0xbbc3aa48,0xba8a3a4f,0x33c6bbfe,0xb89bb8ec,0xba2f3b0e,0x384837e3,0xb913b78b,0xbac23af6,
0x3bf6b4a5,0x367cbbfa,0xae463ba8,0x3b50acb5,0xb913b78b,0xbbe238ec,0x3a2fbb0e,0xb179ba4f,0xae463ba8,0x39843505,0xbbf634a5,0xb9cb3b99,
0x3b3bbadd,0xb505b848,0x36d7381d,0x3b99bac2,0xb9edb0b2,0xbaf63b77,0x395fbbea,0xb7e3b5c2,0xb5643bc3,0x393a3179,0xbb8833c6,0xba0f3be2,
0x3bfeb8c4,0x38ecbbff,0x2a483a6d,0x3a4fa648,0xbbd93aa7,0x2cb5389b,0xb23eb872,0xbbfa3a8a,0x323e3872,0x3bf1b984,0xbbd93aa7,0xafd639cb,
0x3bd9baa7,0x3505bac2,0x323e3872,0x3b99b848,0xb23eb872,0xbaf635c2,0x3bd9baa7,0x37e3bb77,0x3bfeba6d,0x3179b8ec,0xaa4838c4,0x3be2ba4f,
0x36d7badd,0xb9cb3505,0x3b3bb81d,0x3984bb99,0xb95f30b2,0xbbce3bb6,0x39edbbea,0xb303b444,0xbb883bc3,0xb5c23a0f,0xb564b3c6,0xbb77393a,
0xbba83a2f,0xb67c393a,0x34a5b913,0xbb503a0f,0xbb0e3bf6,0x31792fd6,0xb78b2e46,0xbbe23bf1,0xb4a53913,0x3984b732,0xbba83a2f,0xb9cb3b25,
0x378bae46,0x3bcebaf6,0xbb0e3bf6,0xb30337e3,0x3addb9ed,0x38ecb984,0xb81d395f,0x3a4fb9cb,0x3beabb88,0x3732b848,0xb0b23564,0x3b25bac2,
0x3bc3bbfe,0x3444b5c2,0x33c6aa48,0x3bb6bb77,0x3a6dbb3b,0x2cb5b179,0x38c4b6d7,0x3bfabbe2,0xb9a839a8,0xba4f39cb,0x39a8b9a8,0xb8ec3984,
0xb9a839a8,0xbb253ac2,0x39a8b9a8,0xb7323848,0xb9a839a8,0xbbb63b77,0x39a8b9a8,0xb44435c2,0xb9a839a8,0xbbfa3be2,0x39a8b9a8,0xacb53179,
0x381db95f,0x3b50ba0f,0xbadd39ed,0x367cb93a,0x30b2b564,0x3be2bbf1,0xbbea3b88,0xb179afd6,0xb3c62a48,0x39cbbb25,0xbbc33bfe,0xb9843732,
0xb8c436d7,0x3303b7e3,0xba6d3b3b,0xbbce3af6,0xb4a53913,0xbbe23a4f,0x3ba8ba2f,0xb17938ec,0x378bae46,0xb9843b99,0x3b0ebbf6,0x39cbb505,
0x3ba8ba2f,0x33033444,0x34a5b913,0x3bcebbb6,0x3b0ebbf6,0x3b77b93a,0xb78b2e46,0x35c2ba0f,0x2a48b8c4,0x3bfaba8a,0xbbfe3a6d,0xacb5b89b,
0xbb3b381d,0x2fd6b9cb,0xb6d73add,0xbbf13984,0xb9ed3bea,0xbb993848,0x395fb0b2,0xb5053ac2,0x356433c6,0xb7e33b77,0x3b88bbc3,0x3af6b5c2,
0x323e3872,0xbb993ac2,0x3bd9baa7,0x35053848,0x3bd9baa7,0x37e335c2,0xb23eb872,0x3af6bb77,0xb23eb872,0x3a0fbbe2,0xbbd93aa7,0xb93ab179,
0xbbd93aa7,0xba4f2648,0x323e3872,0xb8ec3bff,0xb6d7b81d,0x3ac2baf6,0xbb3b3add,0xb848b7e3,0xb95f3bea,0xbb502cb5,0x39ed30b2,0xb67c3bfa,
0x3b88b3c6,0x31793a4f,0x3564bbc3,0x3be2b8ec,0xaa48ba6d,0x39cbbb99,0xbbfe38c4,0xb984b505,0x3913378b,0xb9843b25,0x3a2fbb0e,0x39cb3732,
0x2e46bba8,0x3bceb7e3,0xbbf634a5,0xb303baf6,0xba2f3b0e,0xbb77acb5,0x3913378b,0xb5c23bfa,0x3bf6b4a5,0x389b38ec,0x2e46bba8,0x3a8aba4f,
0xba6db6d7,0x37e3bb50,0xb8c43b3b,0xbaf6b67c,0x381d39ed,0xb93a3a8a,0x3addb95f,0x3a0f389b,0xb0b2bb88,0x3a4fb984,0xbbea3564,0xb8ecb9cb,
0xb3c63bfe,0xbb253848,0x3bc32a48,0x37323ac2,0x3b64361f,0xb4443b77,0x361fbb64,0x3bb635c2,0xbb64b61f,0x2cb5bbe2,0xb61f3b64,0xbbfab179,
0x3b64361f,0x2fd63bff,0x361fbb64,0x3bf1a648,0xbb64b61f,0xb505bbce,0xb61f3b64,0xbb993303,0xbbeab564,0x2648bb99,0xb0b23b88,0xbbffb505,
0x3bc3aa48,0x38483bb6,0xb3c6bbfe,0x3ac2b444,0xba6d36d7,0xbb50b93a,0x38c43b3b,0xb67c3a0f,0x381db9ed,0x3be22fd6,0xbaddb95f,0xb179bbf1,
0x3bf634a5,0x33033bb6,0xae46bba8,0x3bce3444,0xb913378b,0xbb77ba0f,0x3a2f3b0e,0xb5c2393a,0xae46bba8,0x3a8aafd6,0xbbf6b4a5,0xb89bbbf1,
0x3a2f3b0e,0x26483b25,0x3913b78b,0x3bff3732,0xbb88b3c6,0xb732bbce,0x35643bc3,0xbb25b303,0x2a48ba6d,0x3bb6367c,0xbbfeb8c4,0xb444bb50,
0x3b3b3add,0x2cb53a8a,0x36d7b81d,0x3bfa389b,0xb9ed30b2,0xbbf1b9cb,0x395f3bea,0xafd63984,0x3aa7323e,0x393a3be2,0xb872bbd9,0x3a0f3179,
0x38723bd9,0xb8ec2648,0x3aa7323e,0x3a4f3bff,0xbaa7b23e,0xbb25bbce,0x38723bd9,0xb7323303,0xb872bbd9,0x3444b67c,0xbaa7b23e,0xbbb6bb50,
0xb95fb0b2,0xba8abbf1,0x39ed3bea,0xb89bafd6,0xbb88bbc3,0x2648b732,0xb56433c6,0xbbffbb25,0xaa48b8c4,0x3ac237e3,0xbbfeba6d,0xb848baf6,
0x3b3b381d,0x3b503bfa,0xb6d7badd,0x367cacb5,0x378b2e46,0x3b773bfa,0xbb0ebbf6,0x35c22cb5,0x3ba83a2f,0x389b3a4f,0xb4a5b913,0x3a8a38ec,
0x3b0e3bf6,0x26483505,0x378b2e46,0x3bff3b99,0x34a53913,0xb848b444,0x3ba83a2f,0x3ac23bb6,0xb3c6aa48,0xbbf1bbff,0x3bc33bfe,0xafd6a648,
0xb8c4b6d7,0xbb99bbce,0x3a6d3b3b,0xb505b303,0xbaddb9ed,0xbaf6bb50,0x381d395f,0xb7e3b67c,0xbbeabb88,0xba0fba8a,0x30b23564,0xb93ab89b,
0x3c003c00,0xba4fb9cb,0,0xb8ecb984,0x3c003c00,0xbb25bac2,0,0xb732b848,0x3c003c00,0xbbb6bb77,0,0xb444b5c2,
0x3c003c00,0xbbfabbe2,0,0xacb5b179,0x33c62a48,0x367c393a,0x3bc33bfe,0xbb50ba0f,0x38c436d7,0xb1792fd6,0x3a6d3b3b,0xbbe2bbf1,
0x3add39ed,0xb984b732,0x381d395f,0xb9cbbb25,0x3bea3b88,0xbbcebaf6,0x30b23564,0xb303b7e3,0xbb0ebbf6,0x3be23a4f,0x378b2e46,0x317938ec,
0xb4a5b913,0x39843b99,0x3ba83a2f,0xb9cbb505,0x378b2e46,0xb3033444,0x3b0e3bf6,0xbbcebbb6,0x3ba83a2f,0xbb77b93a,0x34a53913,0xb5c2ba0f,
0xb95fb0b2,0x2cb5b89b,0xb9edbbea,0x3bfa3a8a,0xbb88bbc3,0x3bf13984,0x3564b3c6,0x2fd639cb,0xaa48b8c4,0x35053ac2,0x3bfe3a6d,0xbb99b848,
0x3b3b381d,0xbaf6b5c2,0x36d73add,0xb7e3bb77,0x38723bd9,0xbb99bac2,0xbaa7b23e,0x3505b848,0xbaa7b23e,0x37e3b5c2,0xb872bbd9,0x3af63b77,
0xb872bbd9,0x3a0f3be2,0x3aa7323e,0xb93a3179,0x3aa7323e,0xba4fa648,0x38723bd9,0xb8ecbbff,0x3b8833c6,0xb84837e3,0x35643bc3,0xbac2baf6,
0xaa483a6d,0xb67cbbfa,0xbbfeb8c4,0x3b502cb5,0xbb3bbadd,0x3be238ec,0x36d7b81d,0xb1793a4f,0x39edb0b2,0xb9843505,0x395f3bea,0xb9cbbb99,
0xae46bba8,0x39843b25,0x3bf634a5,0xb9cb3732,0x3a2f3b0e,0xbbceb7e3,0xb913378b,0x3303baf6,0xbbf6b4a5,0x3b77acb5,0xae46bba8,0x35c23bfa,
0x3913b78b,0xb89b38ec,0x3a2f3b0e,0xba8aba4f,0xbbeab564,0x3af6b67c,0x30b2bb88,0x37e33b50,0x3bc3aa48,0xba0f389b,0x33c63bfe,0xb93aba8a,
0xba6d36d7,0x38ecb9cb,0xb8c4bb3b,0x3a4f3984,0x381db9ed,0xb7323ac2,0x3add395f,0xbb25b848,0xb61f3b64,0xb444bb77,0xbb64b61f,0x3bb6b5c2,
0x361fbb64,0x2cb53be2,0x3b64361f,0xbbfa3179,0xb61f3b64,0x2fd6bbff,0xbb64b61f,0x3bf12648,0x361fbb64,0xb5053bce,0x3b64361f,0xbb99b303,
0x3a6d36d7,0xbbff3505,0xb8c43b3b,0xa648bb99,0xb81db9ed,0x3ac23444,0x3addb95f,0xb8483bb6,0x30b23b88,0xb67cba0f,0xbbea3564,0x3b50b93a,
0x33c6bbfe,0xb1793bf1,0x3bc32a48,0xbbe22fd6,0x3a2fbb0e,0xb3033bb6,0x3913378b,0xbbce3444,0xbbf634a5,0x3b77ba0f,0x2e46bba8,0x35c2393a,
0x3913378b,0xba8aafd6,0xba2f3b0e,0x389bbbf1,0x2e46bba8,0xa6483b25,0x3bf6b4a5,0xbbff3732,0xb6d7b81d,0x3b25b303,0x3b3bbadd,0xb7323bce,
0xb95f3bea,0x3444bb50,0xb9edb0b2,0x3bb6b67c,0x3b88b3c6,0xbbfa389b,0xb5643bc3,0x2cb5ba8a,0xaa48ba6d,0x2fd63984,0x3bfeb8c4,0xbbf139cb,
0xbbd93aa7,0x393abbe2,0xb23eb872,0x3a0fb179,0x323e3872,0xb8eca648,0xbbd93aa7,0x3a4fbbff,0x3bd9baa7,0xbb253bce,0x323e3872,0xb732b303,
0xb23eb872,0x3444367c,0x3bd9baa7,0xbbb63b50,0xaa4838c4,0xb89b2fd6,0xbbfe3a6d,0x3a8abbf1,0x3b3bb81d,0xbbff3b25,0xb6d73add,0xa648b732,
0x39edbbea,0xb8483af6,0x395fb0b2,0xbac237e3,0xb564b3c6,0x367c2cb5,0x3b88bbc3,0xbb503bfa,0x3ba8ba2f,0xbb773bfa,0xb4a53913,0xb5c22cb5,
0x3b0ebbf6,0xb89b3a4f,0x378bae46,0xba8a38ec,0x34a5b913,0xa6483505,0x3ba8ba2f,0xbbff3b99,0xb78b2e46,0x3848b444,0x3b0ebbf6,0xbac23bb6,
0x381db95f,0x2fd6a648,0x3addb9ed,0xbbf13bff,0x30b2b564,0x3505b303,0x3beabb88,0xbb993bce,0xb3c62a48,0x37e3b67c,0x3bc3bbfe,0xbaf63b50,
0xb8c436d7,0x393ab89b,0x3a6dbb3b,0xba0f3a8a,0xb9a839a8,0x3bf1bbff,0x39a8b9a8,0xafd62648,0xb9a839a8,0x3b99bbce,0x39a8b9a8,0xb5053303,
0xb9a839a8,0x3af6bb50,0x39a8b9a8,0xb7e3367c,0xb9a839a8,0x3a0fba8a,0x39a8b9a8,0xb93a389b,0xbadd39ed,0x35c2acb5,0xb81d395f,0x3b77bbfa,
0xbbea3b88,0x3a8ab8ec,0xb0b23564,0x389bba4f,0xbbc33bfe,0x3bffbb99,0x33c6aa48,0x2648b505,0xba6d3b3b,0x3ac2bbb6,0x38c4b6d7,0xb8483444,
0x34a5b913,0xba8a3bf1,0xbba83a2f,0x389bafd6,0xb78b2e46,0x26483732,0xbb0e3bf6,0x3bffbb25,0xbba83a2f,0x3ac2b7e3,0xb4a53913,0x3848baf6,
0xbb0e3bf6,0x3b50bbfa,0x378bae46,0xb67cacb5,0x3bfeba6d,0xba0f3179,0x2a48b8c4,0xb93a3be2,0x36d7badd,0xba4f3bff,0xbb3b381d,0x38ec2648,
0xb95f30b2,0x37323303,0xb9ed3bea,0x3b25bbce,0xbb883bc3,0x3bb6bb50,0x356433c6,0xb444b67c,0x323e3872,0x3732bbce,0x3bd9baa7,0xbb253303,
0x3bd9baa7,0xbbb6367c,0xb23eb872,0xb4443b50,0xb23eb872,0xacb53a8a,0xbbd93aa7,0x3bfab89b,0xbbd93aa7,0x3bf1b9cb,0x323e3872,0xafd6b984,
0xbb3b3add,0x3bceb444,0x36d7381d,0x3303bbb6,0x39ed30b2,0xb5c2b93a,0x395fbbea,0xbb773a0f,0x3564bbc3,0xb89b3bf1,0xbb8833c6,0x3a8a2fd6,
0xbbfe38c4,0x3bffb732,0x2a483a6d,0x2648bb25,0xb913b78b,0x26483b99,0xba2f3b0e,0x3bffb505,0xae463ba8,0x3848bbb6,0x3bf6b4a5,0xbac2b444,
0x3a2fbb0e,0xbb50393a,0xb913b78b,0x367c3a0f,0xbbf634a5,0x3be2afd6,0xae463ba8,0x3179bbf1,0x38c4bb3b,0xbbb635c2,0xba6db6d7,0x34443b77,
0xbadd395f,0x3bfab179,0x381d39ed,0xacb5bbe2,0x3beab564,0xbbf1a648,0xb0b2bb88,0xafd63bff,0xbbc3aa48,0x3b993303,0xb3c63bfe,0x3505bbce,
0x3b64361f,0xb7e3bb50,0x361fbb64,0xbaf6367c,0xbb64b61f,0x393a3a8a,0xb61f3b64,0x3a0fb89b,0x3b64361f,0xba4fb984,0x361fbb64,0xb8ec39cb,
0xbb64b61f,0x3b253848,0xb61f3b64,0x3732bac2,0xb0b23b88,0x39cbb732,0x3bea3564,0xb984bb25,0xb3c6bbfe,0xb3033af6,0xbbc32a48,0x3bce37e3,
0x38c43b3b,0xb5c2bbfa,0x3a6db6d7,0xbb772cb5,0xbaddb95f,0x3a8a3a4f,0xb81d39ed,0x389bb8ec,0xbbf6b4a5,0x3ac23af6,0x2e463ba8,0x3848b7e3,
0x3913b78b,0xbb50acb5,0xba2fbb0e,0x367c3bfa,0x2e463ba8,0x3179ba4f,0x3bf634a5,0xbbe2b8ec,0xba2fbb0e,0x39cb3b99,0xb913378b,0x3984b505,
0xb564bbc3,0xb5053848,0xbb88b3c6,0x3b993ac2,0x3bfe38c4,0xbaf6bb77,0x2a48ba6d,0xb7e335c2,0xb6d7381d,0x393ab179,0x3b3b3add,0xba0fbbe2,
0xb95fbbea,0x38ec3bff,0xb9ed30b2,0x3a4f2648,0x3aa7323e,0xbbfaba8a,0xb872bbd9,0xacb5389b,0x38723bd9,0xafd6b9cb,0x3aa7323e,0xbbf1b984,
0xbaa7b23e,0x3b993848,0x38723bd9,0xb505bac2,0xb872bbd9,0x37e33b77,0xbaa7b23e,0x3af635c2,0x39ed3bea,0xb179b8ec,0x395f30b2,0xbbe2ba4f,
0xb56433c6,0x39cb3505,0x3b883bc3,0xb984bb99,0xbbfeba6d,0x3bce3bb6,0x2a4838c4,0x3303b444,0xb6d7badd,0x35c23a0f,0xbb3bb81d,0x3b77393a,
0xb78bae46,0x3b503a0f,0x3b0e3bf6,0xb67cb93a,0xbba8ba2f,0x3be23bf1,0x34a53913,0x3179afd6,0xbb0ebbf6,0x39cb3b25,0xb78bae46,0x39843732,
0xb4a5b913,0x330337e3,0xbba8ba2f,0x3bce3af6,0xbbc3bbfe,0x38ec3984,0xb3c6aa48,0x3a4f39cb,0xba6dbb3b,0x37323848,0xb8c4b6d7,0x3b253ac2,
0xb81db95f,0x344435c2,0xbaddb9ed,0x3bb63b77,0xb0b2b564,0x2cb53179,0xbbeabb88,0x3bfa3be2,0x3c003c00,0x3a4f39cb,0,0x38ec3984,
0x3c003c00,0x3b253ac2,0,0x37323848,0x3c003c00,0x3bb63b77,0,0x344435c2,0x3c003c00,0x3bfa3be2,0,0x2cb53179,
0x33c62a48,0xb67cb93a,0x3bc33bfe,0x3b503a0f,0x38c436d7,0x3179afd6,0x3a6d3b3b,0x3be23bf1,0x3add39ed,0x39843732,0x381d395f,0x39cb3b25,
0x3bea3b88,0x3bce3af6,0x30b23564,0x330337e3,0xbb0ebbf6,0xbbe2ba4f,0x378b2e46,0xb179b8ec,0xb4a5b913,0xb984bb99,0x3ba83a2f,0x39cb3505,
0x378b2e46,0x3303b444,0x3b0e3bf6,0x3bce3bb6,0x3ba83a2f,0x3b77393a,0x34a53913,0x35c23a0f,0xb95fb0b2,0xacb5389b,0xb9edbbea,0xbbfaba8a,
0xbb88bbc3,0xbbf1b984,0x3564b3c6,0xafd6b9cb,0xaa48b8c4,0xb505bac2,0x3bfe3a6d,0x3b993848,0x3b3b381d,0x3af635c2,0x36d73add,0x37e33b77,
0x38723bd9,0x3b993ac2,0xbaa7b23e,0xb5053848,0xbaa7b23e,0xb7e335c2,0xb872bbd9,0xbaf6bb77,0xb872bbd9,0xba0fbbe2,0x3aa7323e,0x393ab179,
0x3aa7323e,0x3a4f2648,0x38723bd9,0x38ec3bff,0x3b8833c6,0x3848b7e3,0x35643bc3,0x3ac23af6,0xaa483a6d,0x367c3bfa,0xbbfeb8c4,0xbb50acb5,
0xbb3bbadd,0xbbe2b8ec,0x36d7b81d,0x3179ba4f,0x39edb0b2,0x3984b505,0x395f3bea,0x39cb3b99,0xae46bba8,0xb984bb25,0x3bf634a5,0x39cbb732,
0x3a2f3b0e,0x3bce37e3,0xb913378b,0xb3033af6,0xbbf6b4a5,0xbb772cb5,0xae46bba8,0xb5c2bbfa,0x3913b78b,0x389bb8ec,0x3a2f3b0e,0x3a8a3a4f,
0xbbeab564,0xbaf6367c,0x30b2bb88,0xb7e3bb50,0x3bc3aa48,0x3a0fb89b,0x33c63bfe,0x393a3a8a,0xba6d36d7,0xb8ec39cb,0xb8c4bb3b,0xba4fb984,
0x381db9ed,0x3732bac2,0x3add395f,0x3b253848,0xb61f3b64,0x34443b77,0xbb64b61f,0xbbb635c2,0x361fbb64,0xacb5bbe2,0x3b64361f,0x3bfab179,
0xb61f3b64,0xafd63bff,0xbb64b61f,0xbbf1a648,0x361fbb64,0x3505bbce,0x3b64361f,0x3b993303,0x3a6d36d7,0x3bffb505,0xb8c43b3b,0x26483b99,
0xb81db9ed,0xbac2b444,0x3addb95f,0x3848bbb6,0x30b23b88,0x367c3a0f,0xbbea3564,0xbb50393a,0x33c6bbfe,0x3179bbf1,0x3bc32a48,0x3be2afd6,
0x3a2fbb0e,0x3303bbb6,0x3913378b,0x3bceb444,0xbbf634a5,0xbb773a0f,0x2e46bba8,0xb5c2b93a,0x3913378b,0x3a8a2fd6,0xba2f3b0e,0xb89b3bf1,
0x2e46bba8,0x2648bb25,0x3bf6b4a5,0x3bffb732,0xb6d7b81d,0xbb253303,0x3b3bbadd,0x3732bbce,0xb95f3bea,0xb4443b50,0xb9edb0b2,0xbbb6367c,
0x3b88b3c6,0x3bfab89b,0xb5643bc3,0xacb53a8a,0xaa48ba6d,0xafd6b984,0x3bfeb8c4,0x3bf1b9cb,0xbbd93aa7,0xb93a3be2,0xb23eb872,0xba0f3179,
0x323e3872,0x38ec2648,0xbbd93aa7,0xba4f3bff,0x3bd9baa7,0x3b25bbce,0x323e3872,0x37323303,0xb23eb872,0xb444b67c,0x3bd9baa7,0x3bb6bb50,
0xaa4838c4,0x389bafd6,0xbbfe3a6d,0xba8a3bf1,0x3b3bb81d,0x3bffbb25,0xb6d73add,0x26483732,0x39edbbea,0x3848baf6,0x395fb0b2,0x3ac2b7e3,
0xb564b3c6,0xb67cacb5,0x3b88bbc3,0x3b50bbfa,0x3ba8ba2f,0x3b77bbfa,0xb4a53913,0x35c2acb5,0x3b0ebbf6,0x389bba4f,0x378bae46,0x3a8ab8ec,
0x34a5b913,0x2648b505,0x3ba8ba2f,0x3bffbb99,0xb78b2e46,0xb8483444,0x3b0ebbf6,0x3ac2bbb6,0x381db95f,0xafd62648,0x3addb9ed,0x3bf1bbff,
0x30b2b564,0xb5053303,0x3beabb88,0x3b99bbce,0xb3c62a48,0xb7e3367c,0x3bc3bbfe,0x3af6bb50,0xb8c436d7,0xb93a389b,0x3a6dbb3b,0x3a0fba8a,
0xb9a839a8,0xbbf13bff,0x39a8b9a8,0x2fd6a648,0xb9a839a8,0xbb993bce,0x39a8b9a8,0x3505b303,0xb9a839a8,0xbaf63b50,0x39a8b9a8,0x37e3b67c,
0xb9a839a8,0xba0f3a8a,0x39a8b9a8,0x393ab89b,0xbadd39ed,0xb5c22cb5,0xb81d395f,0xbb773bfa,0xbbea3b88,0xba8a38ec,0xb0b23564,0xb89b3a4f,
0xbbc33bfe,0xbbff3b99,0x33c6aa48,0xa6483505,0xba6d3b3b,0xbac23bb6,0x38c4b6d7,0x3848b444,0x34a5b913,0x3a8abbf1,0xbba83a2f,0xb89b2fd6,
0xb78b2e46,0xa648b732,0xbb0e3bf6,0xbbff3b25,0xbba83a2f,0xbac237e3,0xb4a53913,0xb8483af6,0xbb0e3bf6,0xbb503bfa,0x378bae46,0x367c2cb5,
0x3bfeba6d,0x3a0fb179,0x2a48b8c4,0x393abbe2,0x36d7badd,0x3a4fbbff,0xbb3b381d,0xb8eca648,0xb95f30b2,0xb732b303,0xb9ed3bea,0xbb253bce,
0xbb883bc3,0xbbb63b50,0x356433c6,0x3444367c,0x323e3872,0xb7323bce,0x3bd9baa7,0x3b25b303,0x3bd9baa7,0x3bb6b67c,0xb23eb872,0x3444bb50,
0xb23eb872,0x2cb5ba8a,0xbbd93aa7,0xbbfa389b,0xbbd93aa7,0xbbf139cb,0x323e3872,0x2fd63984,0xbb3b3add,0xbbce3444,0x36d7381d,0xb3033bb6,
0x39ed30b2,0x35c2393a,0x395fbbea,0x3b77ba0f,0x3564bbc3,0x389bbbf1,0xbb8833c6,0xba8aafd6,0xbbfe38c4,0xbbff3732,0x2a483a6d,0xa6483b25,
0xb913b78b,0xa648bb99,0xba2f3b0e,0xbbff3505,0xae463ba8,0xb8483bb6,0x3bf6b4a5,0x3ac23444,0x3a2fbb0e,0x3b50b93a,0xb913b78b,0xb67cba0f,
0xbbf634a5,0xbbe22fd6,0xae463ba8,0xb1793bf1,0x38c4bb3b,0x3bb6b5c2,0xba6db6d7,0xb444bb77,0xbadd395f,0xbbfa3179,0x381d39ed,0x2cb53be2,
0x3beab564,0x3bf12648,0xb0b2bb88,0x2fd6bbff,0xbbc3aa48,0xbb99b303,0xb3c63bfe,0xb5053bce,0x3b64361f,0x37e33b50,0x361fbb64,0x3af6b67c,
0xbb64b61f,0xb93aba8a,0xb61f3b64,0xba0f389b,0x3b64361f,0x3a4f3984,0x361fbb64,0x38ecb9cb,0xbb64b61f,0xbb25b848,0xb61f3b64,0xb7323ac2,
0xb0b23b88,0xb9cb3732,0x3bea3564,0x39843b25,0xb3c6bbfe,0x3303baf6,0xbbc32a48,0xbbceb7e3,0x38c43b3b,0x35c23bfa,0x3a6db6d7,0x3b77acb5,
0xbaddb95f,0xba8aba4f,0xb81d39ed,0xb89b38ec,0xbbf6b4a5,0xbac2baf6,0x2e463ba8,0xb84837e3,0x3913b78b,0x3b502cb5,0xba2fbb0e,0xb67cbbfa,
0x2e463ba8,0xb1793a4f,0x3bf634a5,0x3be238ec,0xba2fbb0e,0xb9cbbb99,0xb913378b,0xb9843505,0xb564bbc3,0x3505b848,0xbb88b3c6,0xbb99bac2,
0x3bfe38c4,0x3af63b77,0x2a48ba6d,0x37e3b5c2,0xb6d7381d,0xb93a3179,0x3b3b3add,0x3a0f3be2,0xb95fbbea,0xb8ecbbff,0xb9ed30b2,0xba4fa648,
0x3aa7323e,0x3bfa3a8a,0xb872bbd9,0x2cb5b89b,0x38723bd9,0x2fd639cb,0x3aa7323e,0x3bf13984,0xbaa7b23e,0xbb99b848,0x38723bd9,0x35053ac2,
0xb872bbd9,0xb7e3bb77,0xbaa7b23e,0xbaf6b5c2,0x39ed3bea,0x317938ec,0x395f30b2,0x3be23a4f,0xb56433c6,0xb9cbb505,0x3b883bc3,0x39843b99,
0xbbfeba6d,0xbbcebbb6,0x2a4838c4,0xb3033444,0xb6d7badd,0xb5c2ba0f,0xbb3bb81d,0xbb77b93a,0xb78bae46,0xbb50ba0f,0x3b0e3bf6,0x367c393a,
0xbba8ba2f,0xbbe2bbf1,0x34a53913,0xb1792fd6,0xbb0ebbf6,0xb9cbbb25,0xb78bae46,0xb984b732,0xb4a5b913,0xb303b7e3,0xbba8ba2f,0xbbcebaf6,
0xbbc3bbfe,0xb8ecb984,0xb3c6aa48,0xba4fb9cb,0xba6dbb3b,0xb732b848,0xb8c4b6d7,0xbb25bac2,0xb81db95f,0xb444b5c2,0xbaddb9ed,0xbbb6bb77,
0xb0b2b564,0xacb5b179,0xbbeabb88,0xbbfabbe2,0x3c003c00,0x96480000,0x3c003c00,0xa311a248,0x3c003c00,0x9cb69a48,0x3c003c00,0xa452a3db,
0x3c003c00,0x9fdb9e48,0x3c003c00,0xa51ba4b6,0x3c003c00,0xa17fa0b6,0x3bff3c00,0xa5e4a57f,0x3c003c00,0x9fdb0000,0x3bfb3bfc,0xac6aabd9,
0x3bff3c00,0xa5e4a3db,0x3bf93bfa,0xad65ace7,0x3bfe3bff,0xa8e8a7da,0x3bf63bf7,0xae5fade2,0x3bfd3bfe,0xaadea9e3,0x3bf23bf4,0xaf59aedc,
0x3c003c00,0xa3110000,0x3bf03bf4,0xafefaf0e,0x3bfe3bff,0xa94da711,0x3be83bed,0xb0d7b067,0x3bfb3bfd,0xac6aab11,0x3bdf3be4,0xb1b6b147,
0x3bf63bf9,0xae2dad4c,0x3bd43bda,0xb294b226,0x3c003c00,0xa51b0000,0x3bdf3be6,0xb1b6b115,0x3bfc3bfe,0xaba7a91b,0x3bcf3bd7,0xb2f7b257,
0x3bf63bf9,0xae5fad1a,0x3bbc3bc6,0xb41ab396,0x3bec3bf1,0xb074afa4,0x3ba53bb1,0xb4b7b469,0x3bff3c00,0xa6ad0000,0x3bc83bd4,0xb371b2a1,
0x3bfa3bfd,0xad00aaac,0x3bac3bbb,0xb487b420,0x3bef3bf5,0xb029aeaa,0x3b8b3b9d,0xb552b4ed,0x3bde3be7,0xb1cfb0fd,0x3b653b79,0xb61ab5b6,
0x3bff3c00,0xa81f0000,0x3bab3bbc,0xb493b414,0x3bf63bfc,0xae2dac1f,0x3b813b97,0xb58db511,0x3be53bef,0xb122b01d,0x3b4f3b69,0xb682b608,
0x3bcc3bda,0xb328b226,0x3b163b33,0xb76fb6f9,0x3bfe3c00,0xa8e80000,0x3b873ba0,0xb56ab4d5,0x3bf23bfa,0xaf59ace7,0x3b4c3b6b,0xb68db5fd,
0x3bda3be8,0xb219b0e4,0x3b073b2b,0xb7a6b71b,0x3bb73bca,0xb43eb34c,0x3ab63ae0,0xb85ab817,0x3bfe3c00,0xa9b10000,0x3b5e3b80,0xb63cb593,
0x3bee3bf8,0xb042adb0,0x3b103b39,0xb785b6e3,0x3bce3be0,0xb30fb1aa,0x3ab33ae3,0xb85fb812,0x3b9e3bb7,0xb4e7b438,0x3a493a7f,0xb8f3b8ab,
0x3bfd3c00,0xaa7a0000,0x3b2f3b5a,0xb70ab64e,0x3be83bf6,0xb0d7ae78,0x3acb3aff,0xb83ab7c2,0x3bbf3bd6,0xb402b26f,0x3a543a92,0xb8e5b891,
0x3b813ba2,0xb58db4c9,0x39cd3a13,0xb982b935,0x3bfd3c00,0xab430000,0x3afb3b30,0xb7d2b705,0x3be23bf3,0xb16caf40,0x3a7e3abf,0xb8adb84d,
0x3bae3bcb,0xb47bb334,0x39eb3a37,0xb962b909,0x3b603b8a,0xb631b558,0x3946399b,0xba04b9b5,0x3bfc3c00,0xac060000,0x3ac13b02,0xb84ab7b7,
0x3bdc3bf0,0xb201b004,0x3a293a78,0xb91bb8b5,0x3b9c3bc0,0xb4f3b3f7,0x397939d4,0xb9d6b97b,0x3b3d3b70,0xb6d2b5e5,0x38b23918,0xba7aba2b,
0x3bfb3c00,0xac6a0000,0x3a813ad0,0xb8a8b832,0x3bd43bed,0xb294b067,0x39cd3a2b,0xb982b918,0x3b873bb2,0xb56ab45d,0x38fd3969,0xba41b9e5,
0x3b163b53,0xb76fb670,0x3815388c,0xbae1ba95,0x3bfa3c00,0xacce0000,0x3a3d3a99,0xb902b887,0x3bcc3be9,0xb328b0cb,0x396b39d8,0xb9e3b976,
0x3b713ba4,0xb5dfb4bd,0x387a38f6,0xbaa2ba47,0x3aeb3b33,0xb805b6f9,0x36dd37ee,0xbb3abaf3,0x3bf93c00,0xad330000,0x39f43a5e,0xb958b8d8,
0x3bc33be5,0xb3bab12e,0x39023980,0xba3db9d0,0x3b593b95,0xb654b51d,0x37dd387c,0xbaf7baa0,0x3abd3b11,0xb850b780,0x358136b5,0xbb83bb43,
0x3bf83c00,0xad970000,0x39a63a1f,0xb9aab927,0x3bba3be1,0xb426b191,0x38943922,0xba90ba23,0x3b3f3b84,0xb6c6b57c,0x36bb37f9,0xbb42baf0,
0x3a8c3aed,0xb899b802,0x341a3570,0xbbbcbb86,0x3bf73c00,0xadfb0000,0x395439dc,0xb9f8b972,0x3bb03bdc,0xb46fb1f4,0x382038bf,0xbadbba71,
0x3b243b72,0xb737b5da,0x358d36ee,0xbb81bb36,0x3a583ac6,0xb8e0b842,0x31533420,0xbbe3bbbb,0x3bf63c00,0xae5f0000,0x38fd3996,0xba41b9ba,
0x3ba53bd7,0xb4b7b257,0x374e3858,0xbb1ebab8,0x3b073b5f,0xb7a6b637,0x345735da,0xbbb3bb72,0x3a213a9c,0xb924b881,0x2cce3191,0xbbfabbe1,
0x3bf53c00,0xaec30000,0x38a3394d,0xba85b9fe,0x3b9a3bd2,0xb4ffb2b9,0x365437d8,0xbb59baf9,0x3ae83b4b,0xb80ab693,0x323234bd,0xbbd9bba4,
0x39e73a71,0xb966b8bf,0xa4522db0,0xbc00bbf8,0x3bf33c00,0xaf270000,0x38453900,0xbac4ba3f,0x3b8e3bcd,0xb546b31b,0x355236f9,0xbb8bbb33,
0x3ac73b36,0xb840b6ee,0x2f593334,0xbbf2bbcb,0x39aa3a43,0xb9a6b8fb,0xaef51a48,0xbbf4bc00,0x3bf23c00,0xaf8b0000,0x37c838b0,0xbafeba7c,
0x3b813bc7,0xb58db37d,0x344b3614,0xbbb5bb67,0x3aa53b20,0xb874b748,0x288430e4,0xbbffbbe8,0x396b3a13,0xb9e3b935,0xb263ad4c,0xbbd7bbf9,
0x3bf03c00,0xafef0000,0x36ff385d,0xbb32bab5,0x3b733bc1,0xb5d4b3df,0x327c3529,0xbbd6bb93,0x3a813b08,0xb8a8b7a1,0xa9b12d1a,0xbbfebbf9,
0x392939e1,0xba1db96d,0xb49fb160,0xbba9bbe3,0x3bef3c00,0xb0290000,0x36313807,0xbb60bae9,0x3b653bbb,0xb61ab420,0x305b3438,0xbbedbbb7,
0x3a5c3af0,0xb8dbb7f9,0xafef1e48,0xbbf0bc00,0x38e539ad,0xba54b9a4,0xb602b408,0xbb6abbbe,0x3bed3c00,0xb05b0000,0x355e375e,0xbb89bb1a,
0x3b573bb4,0xb65fb451,0x2c6a3288,0xbbfbbbd5,0x3a353ad6,0xb90cb828,0xb27cac51,0xbbd6bbfb,0x389e3976,0xba89b9d8,0xb759b558,0xbb1bbb8a,
0x3beb3c00,0xb08d0000,0x348736aa,0xbbacbb46,0x3b473bad,0xb6a4b481,0x16483099,0xbc00bbeb,0x3a0d3abc,0xb93cb852,0xb47bb080,0xbbaebbec,
0x3855393e,0xbababa0b,0xb850b69e,0xbabdbb49,0x3be93c00,0xb0be0000,0x335935f1,0xbbc9bb6e,0x3b373ba6,0xb6e8b4b1,0xac382d4c,0xbbfcbbf9,
0x39e33aa0,0xb96bb87c,0xb5b1b2d2,0xbb7abbd1,0x380a3905,0xbae8ba3b,0xb8eab7d8,0xba50baf9,0x3be73c00,0xb0f00000,0x319e3534,0xbbe0bb91,
0x3b273b9e,0xb72cb4e1,0xb042257f,0xbbeebc00,0x39b83a83,0xb999b8a6,0xb6ddb48d,0xbb3abbab,0x377a38c9,0xbb13ba69,0xb979b881,0xb9d6ba9c,
0x3be53c00,0xb1220000,0x2fbd3475,0xbbf1bbaf,0x3b163b97,0xb76fb511,0xb263a91b,0xbbd7bbfe,0x398b3a65,0xb9c5b8ce,0xb7feb5ab,0xbaeebb7b,
0x36dd388c,0xbb3aba95,0xb9fcb90e,0xb94fba33,0x3be33c00,0xb1530000,0x2c383365,0xbbfcbbc9,0x3b043b8f,0xb7b2b540,0xb43eae78,0xbbb7bbf6,
0x395d3a47,0xb9f0b8f6,0xb889b6c1,0xba97bb41,0x363c384d,0xbb5ebabf,0xba73b992,0xb8bcb9be,0x3be13c00,0xb1850000,0x217f31db,0xbc00bbdd,
0x3af13b86,0xb7f3b570,0xb546b12e,0xbb8ebbe5,0x392e3a27,0xba19b91d,0xb90cb7cd,0xba35bafc,0x3599380d,0xbb7fbae6,0xbadbba0b,0xb820b93e,
0x3bdf3c00,0xb1b60000,0xa9b1304e,0xbbfebbed,0x3ade3b7d,0xb81ab59f,0xb648b31b,0xbb5cbbcd,0x38fd3a07,0xba41b943,0xb986b867,0xb9c9baae,
0x34f33796,0xbb9cbb0b,0xbb35ba78,0xb6f4b8b5,0x3bdd3c00,0xb1e80000,0xae5f2d7e,0xbbf6bbf8,0x3acb3b74,0xb83ab5ce,0xb742b481,0xbb21bbad,
0x38cc39e5,0xba67b969,0xb9f8b8e2,0xb954ba56,0x344b3710,0xbbb5bb2e,0xbb7fbad9,0xb599b822,0x3bda3c00,0xb2190000,0xb0f028b6,0xbbe7bbff,
0x3ab63b6b,0xb85ab5fd,0xb81ab570,0xbadebb86,0x389939c3,0xba8cb98d,0xba60b956,0xb8d6b9f6,0x33403687,0xbbcbbb4e,0xbbb8bb2e,0xb432b710,
0x3bff3bff,0xa6ada648,0x3bfe3bff,0xa8e8a8b6,0x3bff3bff,0xa776a711,0x3bfe3bfe,0xa94da91b,0x3bff3bff,0xa81fa7da,0x3bfe3bfe,0xa9b1a97f,
0x3bff3bff,0xa884a852,0x3bfe3bfe,0xaa16a9e3,0x3bef3bf1,0xb029afd6,0x3bda3bdd,0xb219b1db,0x3bea3bed,0xb0a6b067,0x3bd43bd7,0xb294b257,
0x3be53be8,0xb122b0e4,0x3bce3bd1,0xb30fb2d2,0x3be03be3,0xb19eb160,0x3bc63bca,0xb389b34c,0x3bc83bce,0xb371b303,0x3b873b91,0xb56ab534,
0x3bba3bc1,0xb426b3df,0x3b733b7d,0xb5d4b59f,0x3bab3bb2,0xb493b45d,0x3b5e3b69,0xb63cb608,0x3b9a3ba2,0xb4ffb4c9,0x3b473b53,0xb6a4b670,
0x3b8b3b99,0xb552b505,0x3b073b1a,0xb7a6b75e,0x3b6f3b7d,0xb5ebb59f,0x3ade3af3,0xb81ab7ee,0x3b4f3b5f,0xb682b637,0x3ab33ac9,0xb85fb83d,
0x3b2c3b3e,0xb715b6cc,0x3a853a9c,0xb8a3b881,0x3b3a3b50,0xb6ddb67c,0x3a5c3a7c,0xb8dbb8b0,0x3b0a3b22,0xb79bb73d,0x3a193a3b,0xb92eb905,
0x3ad53af0,0xb82ab7f9,0x39d239f6,0xb97db956,0x3a9b3ab8,0xb884b858,0x398639ad,0xb9c9b9a4,0x3ad53af6,0xb82ab7e3,0x398b39ba,0xb9c5b996,
0x3a8c3ab1,0xb899b862,0x3929395b,0xba1db9f2,0x3a3d3a65,0xb902b8ce,0x38c138f6,0xba6fba47,0x39e73a13,0xb966b935,0x3855388c,0xbababa95,
0x3a5c3a8a,0xb8dbb89b,0x389938d8,0xba8cba5e,0x39f83a2b,0xb954b918,0x38153858,0xbae1bab8,0x398b39c3,0xb9c5b98d,0x371537a1,0xbb2cbb08,
0x39163951,0xba2db9fa,0x35f73687,0xbb6cbb4e,0x39d23a0f,0xb97db93a,0x371537b7,0xbb2cbb02,0x394f3992,0xb9fcb9be,0x35c83670,0xbb76bb53,
0x38c13909,0xba6fba37,0x346f351d,0xbbb0bb95,0x382a3877,0xbad5baa3,0x3219337d,0xbbdabbc7,0x39373984,0xba11b9cb,0x34cf3593,0xbba1bb80,
0x389438e7,0xba90ba52,0x327c3408,0xbbd6bbbe,0x37c8383d,0xbafebac9,0x2e9130e4,0xbbf5bbe8,0x36543710,0xbb59bb2e,0x16482aac,0xbc00bbfd,
0x388e38ec,0xba93ba4f,0x30d732a1,0xbbe8bbd4,0x3790382d,0xbb0dbad3,0x28e82e14,0xbbfebbf7,0x35eb36c1,0xbb6fbb41,0xaccea4b6,0xbbfabc00,
0x34323511,0xbbb8bb97,0xb201b036,0xbbdcbbee,0x37b23848,0xbb04bac2,0x96482bd9,0xbc00bbfc,0x35df36cc,0xbb71bb3e,0xb010ac1f,0xbbefbbfc,
0x33eb34ed,0xbbc0bb9d,0xb402b20d,0xbbbfbbdb,0x2fef31f4,0xbbf0bbdc,0xb5ebb4f9,0xbb6fbb9b,0x36313732,0xbb60bb25,0xb0f0ad7e,0xbbe7bbf8,
0x341a3529,0xbbbcbb93,0xb49fb31b,0xbba9bbcd,0x2fbd320d,0xbbf1bbdb,0xb6afb5ab,0xbb45bb7b,0xa4522aac,0xbc00bbfd,0xb850b7ac,0xbabdbb05,
0x349f35c2,0xbba9bb77,0xb4dbb365,0xbb9fbbc9,0x308d32ea,0xbbebbbd0,0xb715b5fd,0xbb2cbb6b,0x9fdb2c51,0xbc00bbfb,0xb894b812,0xba90bae3,
0xb109ad4c,0xbbe6bbf9,0xb982b90e,0xb9cdba33,0x32013444,0xbbdcbbb6,0xb721b5f1,0xbb2abb6e,0x26ad2edc,0xbbffbbf4,0xb8adb822,0xba7ebad9,
0xb05bab11,0xbbedbbfd,0xb9aab930,0xb9a6ba17,0xb4b7b2ea,0xbba5bbd0,0xba81ba1b,0xb8a8b92b,0x2d653179,0xbbf9bbe2,0xb89eb807,0xba89bae9,
0xadc99a48,0xbbf8bc00,0xb9afb92b,0xb9a1ba1b,0xb432b1aa,0xbbb8bbe0,0xba93ba27,0xb88eb91d,0xb6d2b587,0xbb3dbb82,0xbb45baf3,0xb6afb7ee,
0xa51b2cb5,0xbc00bbfa,0xb990b900,0xb9c0ba3f,0xb294af40,0xbbd4bbf3,0xba89ba13,0xb89eb935,0xb625b4bd,0xbb63bba4,0xbb47baf0,0xb6a4b7f9,
0xb865b780,0xbab0bb11,0xbbc5bb8f,0xb3a2b540,0xafefa648,0xbbf0bbff,0xba60b9dc,0xb8d6b972,0xb517b31b,0xbb96bbcd,0xbb35bad3,0xb6f4b82d,
0xb7feb693,0xbaeebb4b,0xbbc0bb84,0xb3ebb57c,0xb94ab8ab,0xba00ba7f,0xbbfdbbe9,0xaa7ab0cb,0xb340afd6,0xbbcbbbf1,0xbb0aba99,0xb79bb887,
0xb6d2b540,0xbb3dbb8f,0xbbaebb67,0xb47bb614,0xb8dbb828,0xba5cbad6,0xbbfbbbe0,0xac9cb1aa,0xba15b980,0xb933b9d0,0xbbecbbff,0x30742852,
0xb53ab303,0xbb90bbce,0xbb89bb30,0xb55eb705,0xb83ab6e3,0xbacbbb39,0xbbf2bbca,0xaf8bb34c,0xb9a1b8f6,0xb9afba47,0xbbf5bc00,0x2ec39e48,
0xbac1ba3b,0xb84ab905,0xbb92bbd0,0x352f32ea,0xb6c6b505,0xbb3fbb99,0xbbdcbba0,0xb201b4d5,0xb8fdb838,0xba41bacc,0xbbfebbfb,0x2a16ac83,
0xba50b9b1,0xb8eab99f,0xbbaebbe4,0x347b3147,0xbb4abad9,0xb699b822,0xbaf1bb5d,0x37f33642,0xb820b67c,0xbadbbb50,0xbbffbbe6,0xa884b115,
0xb9afb8f1,0xb9a1ba4b,0xbbd2bbf8,0x32c62db0,0xbae5ba56,0xb80fb8e2,0xbb2abb8c,0x3721354c,0xbbaebb58,0xb47bb659,0xba11baaa,0x3937386d,
0xb8d1b7e3,0xba64baf6,0xbbf2bc00,0x2f8ba248,0xba4db99b,0xb8eeb9b5,0xbb6fbbc1,0x35eb33df,0xbb5cbae3,0xb648b812,0xba6bbafc,0x38c737cd,
0xbbebbbb4,0xb08db451,0xb8f8b9be,0x3a453992,0xb974b89b,0xb9daba8a,0xbbb5bbed,0x344b304e,0xbad5ba33,0xb82ab90e,0xbad8bb58,0x38253659,
0xbbb3bb55,0xb457b665,0xb979ba37,0x39d63909,0xbc00bbed,0x9648b067,0xb764b8a0,0x3b183a87,0xba09b93a,0xb941ba0f,0xbb4abbaf,0x36993475,
0xbb45bab8,0xb6afb858,0xba11babf,0x3937384d,0xbbeabbab,0xb0a6b48d,0xb85ab943,0x3ab63a07,0xbbecbc00,0x30749a48,0xb493b6b5,0x3bab3b43,
0xba8cb9cb,0xb899b984,0xbab3bb46,0x385f36aa,0xbb9cbb28,0xb4f3b726,0xb91fb9fa,0x3a253951,0xbc00bbe4,0xa452b147,0xb631b828,0x3b603ad6,
0xbbb0bbee,0x346f3036,0xae5fb3df,0x3bf63bc1,0xbafeba4f,0xb7c8b8ec,0xb9f4bab5,0x3958385d,0xbbd8bb82,0xb24bb587,0xb80ab90e,0x3ae83a33,
0xbbf3bbfe,0x2f27a97f,0xb2f7b5da,0x3bcf3b72,0xbb4cbbb7,0x368d3438,0x2dc9ac1f,0x3bf83bfc,0xbb5cbac2,0xb648b848,0xb911b9fe,0x3a31394d,
0xbbf9bbc4,0xad33b3ae,0xb5b1b802,0x3b7a3aed,0xbbc5bbf9,0x33a22d1a,0xa94db26f,0x3bfe3bd6,0xbac4bb5d,0x38453642,0x346f2fa4,0x3bb03bf1,
0xbba5bb25,0xb4b7b732,0xb80fb927,0x3ae53a1f,0xbbffbbee,0x2884b036,0xb24bb5b6,0x3bd83b79,0xbb76bbd6,0x35c8326f,0x305ba7da,0x3bed3bff,
0xba19bae0,0x392e3817,0x374234c9,0x3b213ba2,0xbbd9bb77,0xb232b5c2,0xb5ebb832,0x3b6f3ad0,0xbbe8bc00,0x30d7a57f,0xa81fb288,0x3bff3bd5,
0xbb07bb95,0x37a6351d,0x34f33080,0x3b9c3bec,0xb94fba43,0x39fc38fb,0x38ea3780,0x3a503b11,0xbbf8bbb6,0xadc9b444,0xb328b64e,0x3bcc3b5a,
0xbbb7bbf8,0x343e2db0,0x3042a9e3,0x3bee3bfe,0xba7abb36,0x38b236ee,0x379034ed,0x3b0d3b9d,0xb86ab989,0x3aac39c7,0x3a0438fb,0x39463a43,
0xbc00bbe2,0x2311b179,0xac9cb414,0x3bfb3bbc,0xbb6abbd7,0x36023257,0x34b72f40,0x3ba53bf3,0xb9d2babc,0x397d3852,0x38f83775,0x3a453b14,
0xb6ddb8b5,0x3b3a3a78,0x3ae83a0b,0x380a393e,0xbbf2bbfa,0x2f8bacb5,0x2d33af0e,0x3bf93bf4,0xbb04bb9e,0x37b234e1,0x372c3451,0x3b273bb4,
0xb911ba27,0x3a31391d,0x3a0038e2,0x394a3a56,0xb4c3b796,0x3ba33b0b,0x3b8b3ae6,0x3552380d,0x4c004c00,0x26480000,0x4c004c00,0x33113248,
0x4c004c00,0x2cb62a48,0x4c004c00,0x345233db,0x4c004c00,0x2fdb2e48,0x4c004c00,0x351b34b6,0x4c004c00,0x317f30b6,0x4bff4c00,0x35e4357f,
0x4c004c00,0x2fdb0000,0x4bfb4bfc,0x3c6a3bd9,0x4bff4c00,0x35e433db,0x4bf94bfa,0x3d653ce7,0x4bfe4bff,0x38e837da,0x4bf64bf7,0x3e5f3de2,
0x4bfd4bfe,0x3ade39e3,0x4bf24bf4,0x3f593edc,0x4c004c00,0x33110000,0x4bf04bf4,0x3fef3f0e,0x4bfe4bff,0x394d3711,0x4be84bed,0x40d74067,
0x4bfb4bfd,0x3c6a3b11,0x4bdf4be4,0x41b64147,0x4bf64bf9,0x3e2d3d4c,0x4bd44bda,0x42944226,0x4c004c00,0x351b0000,0x4bdf4be6,0x41b64115,
0x4bfc4bfe,0x3ba7391b,0x4bcf4bd7,0x42f74257,0x4bf64bf9,0x3e5f3d1a,0x4bbc4bc6,0x441a4396,0x4bec4bf1,0x40743fa4,0x4ba54bb1,0x44b74469,
0x4bff4c00,0x36ad0000,0x4bc84bd4,0x437142a1,0x4bfa4bfd,0x3d003aac,0x4bac4bbb,0x44874420,0x4bef4bf5,0x40293eaa,0x4b8b4b9d,0x455244ed,
0x4bde4be7,0x41cf40fd,0x4b654b79,0x461a45b6,0x4bff4c00,0x381f0000,0x4bab4bbc,0x44934414,0x4bf64bfc,0x3e2d3c1f,0x4b814b97,0x458d4511,
0x4be54bef,0x4122401d,0x4b4f4b69,0x46824608,0x4bcc4bda,0x43284226,0x4b164b33,0x476f46f9,0x4bfe4c00,0x38e80000,0x4b874ba0,0x456a44d5,
0x4bf24bfa,0x3f593ce7,0x4b4c4b6b,0x468d45fd,0x4bda4be8,0x421940e4,0x4b074b2b,0x47a6471b,0x4bb74bca,0x443e434c,0x4ab64ae0,0x485a4817,
0x4bfe4c00,0x39b10000,0x4b5e4b80,0x463c4593,0x4bee4bf8,0x40423db0,0x4b104b39,0x478546e3,0x4bce4be0,0x430f41aa,0x4ab34ae3,0x485f4812,
0x4b9e4bb7,0x44e74438,0x4a494a7f,0x48f348ab,0x4bfd4c00,0x3a7a0000,0x4b2f4b5a,0x470a464e,0x4be84bf6,0x40d73e78,0x4acb4aff,0x483a47c2,
0x4bbf4bd6,0x4402426f,0x4a544a92,0x48e54891,0x4b814ba2,0x458d44c9,0x49cd4a13,0x49824935,0x4bfd4c00,0x3b430000,0x4afb4b30,0x47d24705,
0x4be24bf3,0x416c3f40,0x4a7e4abf,0x48ad484d,0x4bae4bcb,0x447b4334,0x49eb4a37,0x49624909,0x4b604b8a,0x46314558,0x4946499b,0x4a0449b5,
0x4bfc4c00,0x3c060000,0x4ac14b02,0x484a47b7,0x4bdc4bf0,0x42014004,0x4a294a78,0x491b48b5,0x4b9c4bc0,0x44f343f7,0x497949d4,0x49d6497b,
0x4b3d4b70,0x46d245e5,0x48b24918,0x4a7a4a2b,0x4bfb4c00,0x3c6a0000,0x4a814ad0,0x48a84832,0x4bd44bed,0x42944067,0x49cd4a2b,0x49824918,
0x4b874bb2,0x456a445d,0x48fd4969,0x4a4149e5,0x4b164b53,0x476f4670,0x4815488c,0x4ae14a95,0x4bfa4c00,0x3cce0000,0x4a3d4a99,0x49024887,
0x4bcc4be9,0x432840cb,0x496b49d8,0x49e34976,0x4b714ba4,0x45df44bd,0x487a48f6,0x4aa24a47,0x4aeb4b33,0x480546f9,0x46dd47ee,0x4b3a4af3,
0x4bf94c00,0x3d330000,0x49f44a5e,0x495848d8,0x4bc34be5,0x43ba412e,0x49024980,0x4a3d49d0,0x4b594b95,0x4654451d,0x47dd487c,0x4af74aa0,
0x4abd4b11,0x48504780,0x458146b5,0x4b834b43,0x4bf84c00,0x3d970000,0x49a64a1f,0x49aa4927,0x4bba4be1,0x44264191,0x48944922,0x4a904a23,
0x4b3f4b84,0x46c6457c,0x46bb47f9,0x4b424af0,0x4a8c4aed,0x48994802,0x441a4570,0x4bbc4b86,0x4bf74c00,0x3dfb0000,0x495449dc,0x49f84972,
0x4bb04bdc,0x446f41f4,0x482048bf,0x4adb4a71,0x4b244b72,0x473745da,0x458d46ee,0x4b814b36,0x4a584ac6,0x48e04842,0x41534420,0x4be34bbb,
0x4bf64c00,0x3e5f0000,0x48fd4996,0x4a4149ba,0x4ba54bd7,0x44b74257,0x474e4858,0x4b1e4ab8,0x4b074b5f,0x47a64637,0x445745da,0x4bb34b72,
0x4a214a9c,0x49244881,0x3cce4191,0x4bfa4be1,0x4bf54c00,0x3ec30000,0x48a3494d,0x4a8549fe,0x4b9a4bd2,0x44ff42b9,0x465447d8,0x4b594af9,
0x4ae84b4b,0x480a4693,0x423244bd,0x4bd94ba4,0x49e74a71,0x496648bf,0xb4523db0,0x4c004bf8,0x4bf34c00,0x3f270000,0x48454900,0x4ac44a3f,
0x4b8e4bcd,0x4546431b,0x455246f9,0x4b8b4b33,0x4ac74b36,0x484046ee,0x3f594334,0x4bf24bcb,0x49aa4a43,0x49a648fb,0xbef52a48,0x4bf44c00,
0x4bf24c00,0x3f8b0000,0x47c848b0,0x4afe4a7c,0x4b814bc7,0x458d437d,0x444b4614,0x4bb54b67,0x4aa54b20,0x48744748,0x388440e4,0x4bff4be8,
0x496b4a13,0x49e34935,0xc263bd4c,0x4bd74bf9,0x4bf04c00,0x3fef0000,0x46ff485d,0x4b324ab5,0x4b734bc1,0x45d443df,0x427c4529,0x4bd64b93,
0x4a814b08,0x48a847a1,0xb9b13d1a,0x4bfe4bf9,0x492949e1,0x4a1d496d,0xc49fc160,0x4ba94be3,0x4bef4c00,0x40290000,0x46314807,0x4b604ae9,
0x4b654bbb,0x461a4420,0x405b4438,0x4bed4bb7,0x4a5c4af0,0x48db47f9,0xbfef2e48,0x4bf04c00,0x48e549ad,0x4a5449a4,0xc602c408,0x4b6a4bbe,
0x4bed4c00,0x405b0000,0x455e475e,0x4b894b1a,0x4b574bb4,0x465f4451,0x3c6a4288,0x4bfb4bd5,0x4a354ad6,0x490c4828,0xc27cbc51,0x4bd64bfb,
0x489e4976,0x4a8949d8,0xc759c558,0x4b1b4b8a,0x4beb4c00,0x408d0000,0x448746aa,0x4bac4b46,0x4b474bad,0x46a44481,0x26484099,0x4c004beb,
0x4a0d4abc,0x493c4852,0xc47bc080,0x4bae4bec,0x4855493e,0x4aba4a0b,0xc850c69e,0x4abd4b49,0x4be94c00,0x40be0000,0x435945f1,0x4bc94b6e,
0x4b374ba6,0x46e844b1,0xbc383d4c,0x4bfc4bf9,0x49e34aa0,0x496b487c,0xc5b1c2d2,0x4b7a4bd1,0x480a4905,0x4ae84a3b,0xc8eac7d8,0x4a504af9,
0x4be74c00,0x40f00000,0x419e4534,0x4be04b91,0x4b274b9e,0x472c44e1,0xc042357f,0x4bee4c00,0x49b84a83,0x499948a6,0xc6ddc48d,0x4b3a4bab,
0x477a48c9,0x4b134a69,0xc979c881,0x49d64a9c,0x4be54c00,0x41220000,0x3fbd4475,0x4bf14baf,0x4b164b97,0x476f4511,0xc263b91b,0x4bd74bfe,
0x498b4a65,0x49c548ce,0xc7fec5ab,0x4aee4b7b,0x46dd488c,0x4b3a4a95,0xc9fcc90e,0x494f4a33,0x4be34c00,0x41530000,0x3c384365,0x4bfc4bc9,
0x4b044b8f,0x47b24540,0xc43ebe78,0x4bb74bf6,0x495d4a47,0x49f048f6,0xc889c6c1,0x4a974b41,0x463c484d,0x4b5e4abf,0xca73c992,0x48bc49be,
0x4be14c00,0x41850000,0x317f41db,0x4c004bdd,0x4af14b86,0x47f34570,0xc546c12e,0x4b8e4be5,0x492e4a27,0x4a19491d,0xc90cc7cd,0x4a354afc,
0x4599480d,0x4b7f4ae6,0xcadbca0b,0x4820493e,0x4bdf4c00,0x41b60000,0xb9b1404e,0x4bfe4bed,0x4ade4b7d,0x481a459f,0xc648c31b,0x4b5c4bcd,
0x48fd4a07,0x4a414943,0xc986c867,0x49c94aae,0x44f34796,0x4b9c4b0b,0xcb35ca78,0x46f448b5,0x4bdd4c00,0x41e80000,0xbe5f3d7e,0x4bf64bf8,
0x4acb4b74,0x483a45ce,0xc742c481,0x4b214bad,0x48cc49e5,0x4a674969,0xc9f8c8e2,0x49544a56,0x444b4710,0x4bb54b2e,0xcb7fcad9,0x45994822,
0x4bda4c00,0x42190000,0xc0f038b6,0x4be74bff,0x4ab64b6b,0x485a45fd,0xc81ac570,0x4ade4b86,0x489949c3,0x4a8c498d,0xca60c956,0x48d649f6,
0x43404687,0x4bcb4b4e,0xcbb8cb2e,0x44324710,0x4bd84c00,0x424b0000,0xc2adb248,0x4bd34c00,0x4aa24b62,0x487a462b,0xc88ec659,0x4a934b58,
0x4865499f,0x4ab049b1,0xcabdc9c3,0x4850498d,0x41e845fd,0x4bdd4b6b,0xcbe1cb74,0x418545ce,0x4bd64c00,0x427c0000,0xc432bbd9,0x4bb84bfc,
0x4a8c4b58,0x48994659,0xc8fdc73d,0x4a414b22,0x4830497b,0x4ad149d4,0xcb10ca27,0x4785491d,0x408d4570,0x4beb4b86,0xcbf9cbad,0x3d334481,
0x4bd34c00,0x42ad0000,0xc50bbf0e,0x4b984bf4,0x4a764b4e,0x48b74687,0xc966c80d,0x49e74ae6,0x47f34956,0x4af149f6,0xcb57ca83,0x465f48a6,
0x3e5f44e1,0x4bf64b9e,0xcc00cbd7,0xb17f4257,0x4bd04c00,0x42de0000,0xc5dfc115,0x4b714be6,0x4a604b43,0x48d646b5,0xc9c9c877,0x49864aa3,
0x47854930,0x4b104a17,0xcb92cad6,0x452f4828,0x3b434451,0x4bfd4bb4,0xcbf5cbf3,0xbe913f40,0x4bce4c00,0x430f0000,0xc6afc2a1,0x4b454bd4,
0x4a494b39,0x48f346e3,0xca25c8dd,0x491f4a5a,0x47154909,0x4b2c4a37,0xcbc0cb20,0x43eb4748,0x3311437d,0x4c004bc7,0xcbd9cbff,0xc2323711,
0x4bcb4c00,0x43400000,0xc77ac414,0x4b134bbc,0x4a314b2e,0x49114710,0xca7ac93e,0x48b24a0b,0x46a448e2,0x4b474a56,0xcbe2cb5f,0x416c4637,
0xb7764257,0x4bff4bd7,0xcbaccbfd,0xc487bb75,0x4bc84c00,0x43710000,0xc820c4d5,0x4adb4ba0,0x4a194b22,0x492e473d,0xcac7c99b,0x484049b5,
0x463148ba,0x4b604a74,0xcbf8cb95,0x3dc9451d,0xbc9c412e,0x4bfb4be5,0xcb6fcbeb,0xc5ebc099,0x4bc54c00,0x43a20000,0xc87fc593,0x4a9e4b80,
0x4a004b17,0x494a476a,0xcb0dc9f2,0x4790495b,0x45bc4891,0x4b784a92,0xcc00cbc0,0x317f43f7,0xbf594004,0x4bf24bf0,0xcb21cbca,0xc742c34c,
0x4bc24c00,0x43d30000,0xc8dbc64e,0x4a5c4b5a,0x49e74b0b,0x49664796,0xcb4aca43,0x469948fb,0x45464867,0x4b8e4aae,0xcbfbcbe0,0xbc6a41aa,
0xc1093db0,0x4be64bf8,0xcac4cb9b,0xc845c4f9,0x4bbf4c00,0x44020000,0xc933c705,0x4a154b30,0x49cd4aff,0x498247c2,0xcb7fca8e,0x45994896,
0x44cf483d,0x4ba14ac9,0xcbe9cbf5,0xc0be3eaa,0xc2633aac,0x4bd74bfd,0xca58cb5d,0xc8e0c642,0x4bbc4c00,0x441a0000,0xc986c7b7,0x49c94b02,
0x49b34af3,0x499d47ee,0xcbabcad3,0x4493482d,0x44574812,0x4bb34ae3,0xcbcbcbff,0xc34037da,0xc3ba33db,0x4bc34c00,0xc9dfcb11,0xc970c780,
0x4bb84c00,0x44320000,0xc9d6c832,0x49794ad0,0x49994ae6,0x49b8480d,0xcbcecb11,0x430f4780,0x43ba47cd,0x4bc34afc,0xcb9fcbfe,0xc4dbb97f,
0xc487b57f,0x4bac4c00,0xc958cab8,0xc9f4c858,0x4bb54c00,0x444b0000,0xca21c887,0x49244a99,0x497d4ad9,0x49d24822,0xcbe7cb49,0x40f0469e,
0x42c64775,0x4bd24b14,0xcb68cbf2,0xc60ebf72,0xc52fbb75,0x4b924bfd,0xc8c7ca52,0xca6bc8e7,0x4bb24c00,0x44630000,0xca67c8d8,0x48cc4a5e,
0x49624acc,0x49eb4838,0xcbf8cb79,0x3d9745b6,0x41cf471b,0x4bde4b2b,0xcb24cbdb,0xc737c20d,0xc5d4be14,0x4b734bf7,0xc82ac9e1,0xcad5c96d,
0x4bae4c00,0x447b0000,0xcaa9c927,0x486f4a1f,0x49464abf,0x4a04484d,0xcc00cba2,0x351b44c9,0x40d746c1,0x4be84b41,0xcad5cbb9,0xc82ac42c,
0xc676c036,0x4b524bee,0xc70ac964,0xcb2fc9e9,0x4bab4c00,0x44930000,0xcae5c972,0x480f49dc,0x49294ab1,0x4a1d4862,0xcbfecbc4,0xba1643ae,
0x3fbd4665,0x4bf14b55,0xca7acb8c,0xc8b2c54c,0xc715c160,0x4b2c4be3,0xc5b1c8dd,0xcb7aca5a,0x4ba74c00,0x44ab0000,0xcb1bc9ba,0x47594996,
0x490c4aa3,0x4a354877,0xcbf2cbdf,0xbf5941c3,0x3dc94608,0x4bf84b69,0xca15cb55,0xc933c665,0xc7b2c288,0x4b044bd5,0xc44bc84d,0xcbb5cabf,
0x4ba34c00,0x44c30000,0xcb4cc9fe,0x468d494d,0x48ee4a95,0x4a4d488c,0xcbdecbf1,0xc1cf3fa4,0x3ba745ab,0x4bfc4b7b,0xc9a6cb14,0xc9aac775,
0xc825c3ae,0x4ad84bc4,0xc1b6c76a,0xcbdfcb17,0x4b9f4c00,0x44db0000,0xcb78ca3f,0x45bc4900,0x48d14a87,0x4a6448a0,0xcbc0cbfd,0xc3eb3b75,
0x3776454c,0x4bff4b8c,0xc92ecac9,0xca19c83d,0xc86fc469,0x4aa94bb1,0xbd97c62b,0xcbf8cb62,0x4b9c4c00,0x44f30000,0xcb9eca7c,0x44e748b0,
0x48b24a78,0x4a7a48b5,0xcb9acc00,0xc4ffaa48,0xa64844ed,0x4c004b9d,0xc8adca74,0xca7ec8ba,0xc8b7c4f9,0x4a764b9b,0x2cb6c4e1,0xcc00cb9e,
0x4b984c00,0x450b0000,0xcbbdcab5,0x440e485d,0x48944a69,0x4a9048c9,0xcb6acbfc,0xc602bc1f,0xb81f448d,0x4bff4bab,0xc825ca17,0xcad8c930,
0xc8fdc587,0x4a414b82,0x3e2dc31b,0xcbf6cbcd,0x4b944c00,0x45230000,0xcbd7cae9,0x42634807,0x48744a5a,0x4aa548dd,0xcb32cbf0,0xc6ffc004,
0xbc06442c,0x4bfc4bb9,0xc72cc9b1,0xcb27c99f,0xc941c614,0x4a094b67,0x4201c067,0xcbdccbed,0x4b904c00,0x453a0000,0xcbeacb1a,0x40a6475e,
0x48554a4b,0x4aba48f1,0xcaf1cbdc,0xc7f3c1f4,0xbdfb4396,0x4bf74bc6,0xc602c943,0xcb6aca07,0xc982c69e,0x49cd4b49,0x446fbaac,0xcbb0cbfd,
0x4b8b4c00,0x45520000,0xcbf8cb46,0x3dc946aa,0x48354a3b,0x4ace4905,0xcaa9cbc1,0xc86fc3df,0xbfef42d2,0x4bf04bd1,0xc4cfc8ce,0xcba1ca65,
0xc9c0c726,0x49904b28,0x45d43852,0xcb73cbff,0x4b874c00,0x456a0000,0xcbffcb6e,0x388445f1,0x48154a2b,0x4ae14918,0xca58cb9e,0xc8e0c4e1,
0xc0f0420d,0x4be74bdb,0xc328c852,0xcbcccabc,0xc9fcc7ac,0x494f4b05,0x472c3fa4,0xcb27cbf1,0x4b834c00,0x45810000,0xcc00cb91,0xb51b4534,
0x47e84a1b,0x4af4492b,0xca00cb74,0xc94ac5ce,0xc1e84147,0x4bdd4be4,0xc0a6c7a1,0xcbeacb08,0xca35c817,0x490c4ae0,0x483a4288,0xcacbcbd5,
0x4b7f4c00,0x45990000,0xcbfacbaf,0xbcce4475,0x47a64a0b,0x4b07493e,0xc9a1cb43,0xc9afc6b5,0xc2de4080,0x4bd04bec,0xbc38c693,0xcbfccb4b,
0xca6bc858,0x48c74ab8,0x48d64499,0xca60cbaa,0x4b7a4c00,0x45b10000,0xcbefcbc9,0xc0294365,0x476449fa,0x4b184951,0xc93ccb0b,0xca0dc796,
0xc3d33f72,0x4bc24bf2,0x3311c57c,0xcc00cb84,0xca9ec896,0x487f4a8e,0x496645e5,0xc9e7cb70,0x4b764c00,0x45c80000,0xcbddcbdd,0xc1e841db,
0x472149e9,0x4b2a4964,0xc8d1cacc,0xca64c838,0xc4633de2,0x4bb24bf7,0x3dfbc45d,0xcbf7cbb2,0xcacec8d3,0x48354a62,0x49eb4726,0xc962cb28,
0x4b714c00,0x45df0000,0xcbc5cbed,0xc3a2404e,0x46dd49d8,0x4b3a4976,0xc85fca87,0xcab3c8a0,0xc4db3c51,0x4b9f4bfb,0x4185c26f,0xcbe1cbd6,
0xcafbc90e,0x47d24a33,0x4a64482d,0xc8d1cad3,0x4b6c4c00,0x45f70000,0xcba7cbf8,0xc4ab3d7e,0x469949c7,0x4b4a4989,0xc7d2ca3b,0xcafbc905,
0xc552397f,0x4b8b4bfe,0x4402c01d,0xcbbfcbef,0xcb24c948,0x47374a02,0x4ace48bf,0xc835ca71,0x4b684c00,0x460e0000,0xcb83cbff,0xc58138b6,
0x465449b5,0x4b59499b,0xc6ddc9e9,0xcb3ac964,0xc5c834b6,0x4b764c00,0x453abb11,0xcb90cbfd,0xcb4ac980,0x469949d0,0x4b2a4948,0xc721ca02,
0x2c002c00,0x2c002c00,0x2c002c00,0x2c002c00,0x2b642c00,0x261f29a8,0xa61f0000,0xab64a9a8,0x29a82c00,0xa9a80000,0xa9a8ac00,0x29a80000,
0x261f2c00,0xab64a9a8,0x2b640000,0xa61f29a8,0x2c00,0xac00,0x2c00,0xac00,0xa61f2c00,0x2b64a9a8,0xab640000,0x261f29a8,
0xa9a82c00,0x29a80000,0x29a8ac00,0xa9a80000,0xab642c00,0xa61f29a8,0x261f0000,0x2b64a9a8,0,0,0,0,
0x261f0000,0x2b6429a8,0x2b642c00,0x261f29a8,0x29a80000,0x29a82c00,0xa9a80000,0xa9a8ac00,0x2b640000,0xa61f29a8,0xa61fac00,0x2b6429a8,
0x2c000000,0xac000000,0x2c000000,0xac000000,0x2b640000,0xa61fa9a8,0xa61f2c00,0x2b64a9a8,0x29a80000,0x29a8ac00,0xa9a80000,0xa9a82c00,
0x261f0000,0x2b64a9a8,0x2b64ac00,0x261fa9a8,0xac002c00,0xac002c00,0xac002c00,0xac002c00,0xab642c00,0xa61f29a8,0x261f0000,0x2b64a9a8,
0xa9a82c00,0x29a80000,0x29a8ac00,0xa9a80000,0xa61f2c00,0x2b64a9a8,0xab640000,0x261f29a8,0x2c00,0xac00,0x2c00,0xac00,
0x261f2c00,0xab64a9a8,0x2b640000,0xa61f29a8,0x29a82c00,0xa9a80000,0xa9a8ac00,0x29a80000,0x2b642c00,0x261f29a8,0xa61f0000,0xab64a9a8,
0,0,0,0,0xa61f0000,0xab6429a8,0xab642c00,0xa61f29a8,0xa9a80000,0xa9a82c00,0x29a80000,0x29a8ac00,
0xab640000,0x261f29a8,0x261fac00,0xab6429a8,0xac000000,0x2c000000,0xac000000,0x2c000000,0xab640000,0x261fa9a8,0x261f2c00,0xab64a9a8,
0xa9a80000,0xa9a8ac00,0x29a80000,0x29a82c00,0xa61f0000,0xab64a9a8,0xab64ac00,0xa61fa9a8,0,0,0,0,
0xa61f0000,0xab64a9a8,0xab64ac00,0xa61fa9a8,0xa9a80000,0xa9a8ac00,0x29a80000,0x29a82c00,0xab640000,0x261fa9a8,0x261f2c00,0xab64a9a8,
0xac000000,0x2c000000,0xac000000,0x2c000000,0xab640000,0x261f29a8,0x261fac00,0xab6429a8,0xa9a80000,0xa9a82c00,0x29a80000,0x29a8ac00,
0xa61f0000,0xab6429a8,0xab642c00,0xa61f29a8,0x2c002c00,0x2c002c00,0x2c002c00,0x2c002c00,0x2b642c00,0x261f29a8,0xa61f0000,0xab64a9a8,
0x29a82c00,0xa9a80000,0xa9a8ac00,0x29a80000,0x261f2c00,0xab64a9a8,0x2b640000,0xa61f29a8,0x2c00,0xac00,0x2c00,0xac00,
0xa61f2c00,0x2b64a9a8,0xab640000,0x261f29a8,0xa9a82c00,0x29a80000,0x29a8ac00,0xa9a80000,0xab642c00,0xa61f29a8,0x261f0000,0x2b64a9a8,
0,0,0,0,0x261f0000,0x2b64a9a8,0x2b64ac00,0x261fa9a8,0x29a80000,0x29a8ac00,0xa9a80000,0xa9a82c00,
0x2b640000,0xa61fa9a8,0xa61f2c00,0x2b64a9a8,0x2c000000,0xac000000,0x2c000000,0xac000000,0x2b640000,0xa61f29a8,0xa61fac00,0x2b6429a8,
0x29a80000,0x29a82c00,0xa9a80000,0xa9a8ac00,0x261f0000,0x2b6429a8,0x2b642c00,0x261f29a8,0xac002c00,0xac002c00,0xac002c00,0xac002c00,
0xab642c00,0xa61f29a8,0x261f0000,0x2b64a9a8,0xa9a82c00,0x29a80000,0x29a8ac00,0xa9a80000,0xa61f2c00,0x2b64a9a8,0xab640000,0x261f29a8,
0x2c00,0xac00,0x2c00,0xac00,0x261f2c00,0xab64a9a8,0x2b640000,0xa61f29a8,0x29a82c00,0xa9a80000,0xa9a8ac00,0x29a80000,
0x2b642c00,0x261f29a8,0xa61f0000,0xab64a9a8,0x2c002c00,0x2c002c00,0x2c002c00,0x2c002c00,0xab64ac00,0xa61fa9a8,0x261f0000,0x2b6429a8,
0x29a82c00,0xa9a80000,0xa9a8ac00,0x29a80000,0xa61fac00,0x2b6429a8,0xab640000,0x261fa9a8,0x2c00,0xac00,0x2c00,0xac00,
0x261fac00,0xab6429a8,0x2b640000,0xa61fa9a8,0xa9a82c00,0x29a80000,0x29a8ac00,0xa9a80000,0x2b64ac00,0x261fa9a8,0xa61f0000,0xab6429a8,
0,0,0,0,0xa61f0000,0xab64a9a8,0xab64ac00,0xa61fa9a8,0x29a80000,0x29a82c00,0xa9a80000,0xa9a8ac00,
0xab640000,0x261fa9a8,0x261f2c00,0xab64a9a8,0x2c000000,0xac000000,0x2c000000,0xac000000,0xab640000,0x261f29a8,0x261fac00,0xab6429a8,
0x29a80000,0x29a8ac00,0xa9a80000,0xa9a82c00,0xa61f0000,0xab6429a8,0xab642c00,0xa61f29a8,0xac002c00,0xac002c00,0xac002c00,0xac002c00,
0x2b64ac00,0x261fa9a8,0xa61f0000,0xab6429a8,0xa9a82c00,0x29a80000,0x29a8ac00,0xa9a80000,0x261fac00,0xab6429a8,0x2b640000,0xa61fa9a8,
0x2c00,0xac00,0x2c00,0xac00,0xa61fac00,0x2b6429a8,0xab640000,0x261fa9a8,0x29a82c00,0xa9a80000,0xa9a8ac00,0x29a80000,
0xab64ac00,0xa61fa9a8,0x261f0000,0x2b6429a8,0,0,0,0,0x261f0000,0x2b64a9a8,0x2b64ac00,0x261fa9a8,
0xa9a80000,0xa9a82c00,0x29a80000,0x29a8ac00,0x2b640000,0xa61fa9a8,0xa61f2c00,0x2b64a9a8,0xac000000,0x2c000000,0xac000000,0x2c000000,
0x2b640000,0xa61f29a8,0xa61fac00,0x2b6429a8,0xa9a80000,0xa9a8ac00,0x29a80000,0x29a82c00,0x261f0000,0x2b6429a8,0x2b642c00,0x261f29a8,
0,0,0,0,0x261f0000,0x2b6429a8,0x2b642c00,0x261f29a8,0xa9a80000,0xa9a8ac00,0x29a80000,0x29a82c00,
0x2b640000,0xa61f29a8,0xa61fac00,0x2b6429a8,0xac000000,0x2c000000,0xac000000,0x2c000000,0x2b640000,0xa61fa9a8,0xa61f2c00,0x2b64a9a8,
0xa9a80000,0xa9a82c00,0x29a80000,0x29a8ac00,0x261f0000,0x2b64a9a8,0x2b64ac00,0x261fa9a8,0x2c002c00,0x2c002c00,0x2c002c00,0x2c002c00,
0xab64ac00,0xa61fa9a8,0x261f0000,0x2b6429a8,0x29a82c00,0xa9a80000,0xa9a8ac00,0x29a80000,0xa61fac00,0x2b6429a8,0xab640000,0x261fa9a8,
0x2c00,0xac00,0x2c00,0xac00,0x261fac00,0xab6429a8,0x2b640000,0xa61fa9a8,0xa9a82c00,0x29a80000,0x29a8ac00,0xa9a80000,
0x2b64ac00,0x261fa9a8,0xa61f0000,0xab6429a8,0,0,0,0,0xa61f0000,0xab6429a8,0xab642c00,0xa61f29a8,
0x29a80000,0x29a8ac00,0xa9a80000,0xa9a82c00,0xab640000,0x261f29a8,0x261fac00,0xab6429a8,0x2c000000,0xac000000,0x2c000000,0xac000000,
0xab640000,0x261fa9a8,0x261f2c00,0xab64a9a8,0x29a80000,0x29a82c00,0xa9a80000,0xa9a8ac00,0xa61f0000,0xab64a9a8,0xab64ac00,0xa61fa9a8,
0xac002c00,0xac002c00,0xac002c00,0xac002c00,0x2b64ac00,0x261fa9a8,0xa61f0000,0xab6429a8,0xa9a82c00,0x29a80000,0x29a8ac00,0xa9a80000,
0x261fac00,0xab6429a8,0x2b640000,0xa61fa9a8,0x2c00,0xac00,0x2c00,0xac00,0xa61fac00,0x2b6429a8,0xab640000,0x261fa9a8,
0x29a82c00,0xa9a80000,0xa9a8ac00,0x29a80000,0xab64ac00,0xa61fa9a8,0x261f0000,0x2b6429a8,0x2bd92c00,0x2aa72b64,0x287229a8,0x223e261f,
0x2aa72c00,0xa23e261f,0xabd9a9a8,0xa872ab64,0x28722c00,0xabd9a61f,0x223ea9a8,0x2aa72b64,0x223e2c00,0xa872ab64,0x2aa729a8,0xabd9a61f,
0xa23e2c00,0x2872ab64,0xaaa729a8,0x2bd9a61f,0xa8722c00,0x2bd9a61f,0xa23ea9a8,0xaaa72b64,0xaaa72c00,0x223e261f,0x2bd9a9a8,0x2872ab64,
0xabd92c00,0xaaa72b64,0xa87229a8,0xa23e261f,0x223e0000,0x2872261f,0x2aa729a8,0x2bd92b64,0x28720000,0x2bd92b64,0x223e29a8,0xaaa7a61f,
0x2aa70000,0x223e2b64,0xabd9a9a8,0x2872a61f,0x2bd90000,0xaaa7261f,0x2872a9a8,0xa23e2b64,0x2bd90000,0xaaa7a61f,0x287229a8,0xa23eab64,
0x2aa70000,0x223eab64,0xabd929a8,0x2872261f,0x28720000,0x2bd9ab64,0x223ea9a8,0xaaa7261f,0x223e0000,0x2872a61f,0x2aa7a9a8,0x2bd9ab64,
0xabd92c00,0xaaa72b64,0xa87229a8,0xa23e261f,0xaaa72c00,0x223e261f,0x2bd9a9a8,0x2872ab64,0xa8722c00,0x2bd9a61f,0xa23ea9a8,0xaaa72b64,
0xa23e2c00,0x2872ab64,0xaaa729a8,0x2bd9a61f,0x223e2c00,0xa872ab64,0x2aa729a8,0xabd9a61f,0x28722c00,0xabd9a61f,0x223ea9a8,0x2aa72b64,
0x2aa72c00,0xa23e261f,0xabd9a9a8,0xa872ab64,0x2bd92c00,0x2aa72b64,0x287229a8,0x223e261f,0xa23e0000,0xa872261f,0xaaa729a8,0xabd92b64,
0xa8720000,0xabd92b64,0xa23e29a8,0x2aa7a61f,0xaaa70000,0xa23e2b64,0x2bd9a9a8,0xa872a61f,0xabd90000,0x2aa7261f,0xa872a9a8,0x223e2b64,
0xabd90000,0x2aa7a61f,0xa87229a8,0x223eab64,0xaaa70000,0xa23eab64,0x2bd929a8,0xa872261f,0xa8720000,0xabd9ab64,0xa23ea9a8,0x2aa7261f,
0xa23e0000,0xa872a61f,0xaaa7a9a8,0xabd9ab64,0xa23e0000,0xa872a61f,0xaaa7a9a8,0xabd9ab64,0xa8720000,0xabd9ab64,0xa23ea9a8,0x2aa7261f,
0xaaa70000,0xa23eab64,0x2bd929a8,0xa872261f,0xabd90000,0x2aa7a61f,0xa87229a8,0x223eab64,0xabd90000,0x2aa7261f,0xa872a9a8,0x223e2b64,
0xaaa70000,0xa23e2b64,0x2bd9a9a8,0xa872a61f,0xa8720000,0xabd92b64,0xa23e29a8,0x2aa7a61f,0xa23e0000,0xa872261f,0xaaa729a8,0xabd92b64,
0x2bd92c00,0x2aa72b64,0x287229a8,0x223e261f,0x2aa72c00,0xa23e261f,0xabd9a9a8,0xa872ab64,0x28722c00,0xabd9a61f,0x223ea9a8,0x2aa72b64,
0x223e2c00,0xa872ab64,0x2aa729a8,0xabd9a61f,0xa23e2c00,0x2872ab64,0xaaa729a8,0x2bd9a61f,0xa8722c00,0x2bd9a61f,0xa23ea9a8,0xaaa72b64,
0xaaa72c00,0x223e261f,0x2bd9a9a8,0x2872ab64,0xabd92c00,0xaaa72b64,0xa87229a8,0xa23e261f,0x223e0000,0x2872a61f,0x2aa7a9a8,0x2bd9ab64,
0x28720000,0x2bd9ab64,0x223ea9a8,0xaaa7261f,0x2aa70000,0x223eab64,0xabd929a8,0x2872261f,0x2bd90000,0xaaa7a61f,0x287229a8,0xa23eab64,
0x2bd90000,0xaaa7261f,0x2872a9a8,0xa23e2b64,0x2aa70000,0x223e2b64,0xabd9a9a8,0x2872a61f,0x28720000,0x2bd92b64,0x223e29a8,0xaaa7a61f,
0x223e0000,0x2872261f,0x2aa729a8,0x2bd92b64,0xabd92c00,0xaaa72b64,0xa87229a8,0xa23e261f,0xaaa72c00,0x223e261f,0x2bd9a9a8,0x2872ab64,
0xa8722c00,0x2bd9a61f,0xa23ea9a8,0xaaa72b64,0xa23e2c00,0x2872ab64,0xaaa729a8,0x2bd9a61f,0x223e2c00,0xa872ab64,0x2aa729a8,0xabd9a61f,
0x28722c00,0xabd9a61f,0x223ea9a8,0x2aa72b64,0x2aa72c00,0xa23e261f,0xabd9a9a8,0xa872ab64,0x2bd92c00,0x2aa72b64,0x287229a8,0x223e261f,
0xa23e0000,0xa872a61f,0xaaa7a9a8,0xabd9ab64,0x28720000,0x2bd92b64,0x223e29a8,0xaaa7a61f,0xaaa70000,0xa23eab64,0x2bd929a8,0xa872261f,
0x2bd90000,0xaaa7261f,0x2872a9a8,0xa23e2b64,0xabd90000,0x2aa7261f,0xa872a9a8,0x223e2b64,0x2aa70000,0x223eab64,0xabd929a8,0x2872261f,
0xa8720000,0xabd92b64,0xa23e29a8,0x2aa7a61f,0x223e0000,0x2872a61f,0x2aa7a9a8,0x2bd9ab64,0x2bd92c00,0x2aa72b64,0x287229a8,0x223e261f,
0xaaa7ac00,0x223ea61f,0x2bd929a8,0x28722b64,0x28722c00,0xabd9a61f,0x223ea9a8,0x2aa72b64,0xa23eac00,0x28722b64,0xaaa7a9a8,0x2bd9261f,
0xa23e2c00,0x2872ab64,0xaaa729a8,0x2bd9a61f,0x2872ac00,0xabd9261f,0x223e29a8,0x2aa7ab64,0xaaa72c00,0x223e261f,0x2bd9a9a8,0x2872ab64,
0x2bd9ac00,0x2aa7ab64,0x2872a9a8,0x223ea61f,0x223e0000,0x2872a61f,0x2aa7a9a8,0x2bd9ab64,0xa8720000,0xabd92b64,0xa23e29a8,0x2aa7a61f,
0x2aa70000,0x223eab64,0xabd929a8,0x2872261f,0xabd90000,0x2aa7261f,0xa872a9a8,0x223e2b64,0x2bd90000,0xaaa7261f,0x2872a9a8,0xa23e2b64,
0xaaa70000,0xa23eab64,0x2bd929a8,0xa872261f,0x28720000,0x2bd92b64,0x223e29a8,0xaaa7a61f,0xa23e0000,0xa872a61f,0xaaa7a9a8,0xabd9ab64,
0xabd92c00,0xaaa72b64,0xa87229a8,0xa23e261f,0x2aa7ac00,0xa23ea61f,0xabd929a8,0xa8722b64,0xa8722c00,0x2bd9a61f,0xa23ea9a8,0xaaa72b64,
0x223eac00,0xa8722b64,0x2aa7a9a8,0xabd9261f,0x223e2c00,0xa872ab64,0x2aa729a8,0xabd9a61f,0xa872ac00,0x2bd9261f,0xa23e29a8,0xaaa7ab64,
0x2aa72c00,0xa23e261f,0xabd9a9a8,0xa872ab64,0xabd9ac00,0xaaa7ab64,0xa872a9a8,0xa23ea61f,0xabd9ac00,0xaaa7ab64,0xa872a9a8,0xa23ea61f,
0x2aa72c00,0xa23e261f,0xabd9a9a8,0xa872ab64,0xa872ac00,0x2bd9261f,0xa23e29a8,0xaaa7ab64,0x223e2c00,0xa872ab64,0x2aa729a8,0xabd9a61f,
0x223eac00,0xa8722b64,0x2aa7a9a8,0xabd9261f,0xa8722c00,0x2bd9a61f,0xa23ea9a8,0xaaa72b64,0x2aa7ac00,0xa23ea61f,0xabd929a8,0xa8722b64,
0xabd92c00,0xaaa72b64,0xa87229a8,0xa23e261f,0xa23e0000,0xa872a61f,0xaaa7a9a8,0xabd9ab64,0x28720000,0x2bd92b64,0x223e29a8,0xaaa7a61f,
0xaaa70000,0xa23eab64,0x2bd929a8,0xa872261f,0x2bd90000,0xaaa7261f,0x2872a9a8,0xa23e2b64,0xabd90000,0x2aa7261f,0xa872a9a8,0x223e2b64,
0x2aa70000,0x223eab64,0xabd929a8,0x2872261f,0xa8720000,0xabd92b64,0xa23e29a8,0x2aa7a61f,0x223e0000,0x2872a61f,0x2aa7a9a8,0x2bd9ab64,
0x2bd9ac00,0x2aa7ab64,0x2872a9a8,0x223ea61f,0xaaa72c00,0x223e261f,0x2bd9a9a8,0x2872ab64,0x2872ac00,0xabd9261f,0x223e29a8,0x2aa7ab64,
0xa23e2c00,0x2872ab64,0xaaa729a8,0x2bd9a61f,0xa23eac00,0x28722b64,0xaaa7a9a8,0x2bd9261f,0x28722c00,0xabd9a61f,0x223ea9a8,0x2aa72b64,
0xaaa7ac00,0x223ea61f,0x2bd929a8,0x28722b64,0x2bd92c00,0x2aa72b64,0x287229a8,0x223e261f,0x223e0000,0x2872a61f,0x2aa7a9a8,0x2bd9ab64,
0xa8720000,0xabd92b64,0xa23e29a8,0x2aa7a61f,0x2aa70000,0x223eab64,0xabd929a8,0x2872261f,0xabd90000,0x2aa7261f,0xa872a9a8,0x223e2b64,
0x2bd90000,0xaaa7261f,0x2872a9a8,0xa23e2b64,0xaaa70000,0xa23eab64,0x2bd929a8,0xa872261f,0x28720000,0x2bd92b64,0x223e29a8,0xaaa7a61f,
0xa23e0000,0xa872a61f,0xaaa7a9a8,0xabd9ab64,0x27fe2800,0x96480000,0x273b2764,0xa2d7a21f,0x27ea27f6,0x9cb29a46,0x26dd270e,0xa41da38b,
0x27c327d9,0x9fc69e3e,0x266d26a7,0xa4c4a472,0x278827a8,0xa164a0a5,0x25ed262f,0xa55fa513,0x27c32800,0x9fc60000,0xa4c4a21f,0xa66da764,
0x25ed270e,0xa55fa38b,0xa73ba62f,0xa2d7a513,0x21642472,0xa788a6a7,0xa7fea7d9,0x16489e3e,0x9cb21a46,0xa7eaa7f6,0xa6dda7a8,0x241d20a5,
0x273b2800,0xa2d70000,0xa55fa764,0x25ed221f,0x1fc62513,0xa7c3a62f,0x1cb2a0a5,0x27ea27a8,0xa4c49e3e,0xa66da7d9,0x26dd2472,0x241d26a7,
0xa7fea70e,0x9648a38b,0x278827f6,0xa1641a46,0x266d2800,0xa4c40000,0x26dd221f,0x241d2764,0xa16420a5,0xa788a7a8,0x25ed27f6,0xa55f9a46,
0xa7fea6a7,0x1648a472,0xa2d71e3e,0xa73ba7d9,0x9fc6a62f,0x27c32513,0xa7eaa70e,0x1cb2a38b,0x255f2800,0xa5ed0000,0x21642764,0xa788a21f,
0xa66d9a46,0xa4c4a7f6,0xa7c3a38b,0x9fc6a70e,0xa41da7d9,0x26dd1e3e,0x9cb2a6a7,0x27ea2472,0x273b20a5,0x22d727a8,0x27fe2513,0x1648262f,
0x241d2800,0xa6dd0000,0xa7eaa21f,0x9cb2a764,0xa7fea38b,0x9648a70e,0x2164a513,0x2788262f,0x22d7a472,0x273b26a7,0x255f27d9,0xa5ed1e3e,
0x24c427f6,0xa66d1a46,0xa7c3a0a5,0x9fc6a7a8,0x21642800,0xa7880000,0x1648a764,0x27fe221f,0xa6dda62f,0x241da513,0x24c427a8,0xa66d20a5,
0x27ea1e3e,0x1cb227d9,0xa7c3a472,0x1fc6a6a7,0xa55f238b,0xa5eda70e,0x273b9a46,0x22d727f6,0x1cb22800,0xa7ea0000,0x27c3221f,0x9fc62764,
0xa2d7a7a8,0x273ba0a5,0xa7fe9a46,0x9648a7f6,0x255f26a7,0xa5ed2472,0x27889e3e,0x216427d9,0xa6dda513,0x241da62f,0xa66d238b,0xa4c4a70e,
0x96482800,0xa7fe0000,0xa2d72764,0xa73ba21f,0x1cb2a7f6,0x27ea1a46,0x241da70e,0x26dd238b,0x9fc627d9,0xa7c39e3e,0xa4c426a7,0xa66da472,
0x2164a7a8,0x278820a5,0x255fa62f,0x25ed2513,0x9fc62800,0xa7c30000,0xa66da21f,0x24c4a764,0x255fa70e,0x25ed238b,0x22d7262f,0xa73b2513,
0xa7882472,0xa164a6a7,0x1648a7d9,0x27fe9e3e,0x27ea9a46,0x9cb227f6,0xa41d27a8,0xa6dda0a5,0xa2d72800,0xa73b0000,0x25eda764,0x255f221f,
0x27c3a513,0x1fc6262f,0xa7ea20a5,0x1cb2a7a8,0xa66d9e3e,0x24c4a7d9,0x241d2472,0xa6dd26a7,0x1648270e,0xa7fe238b,0x2164a7f6,0x27889a46,
0xa4c42800,0xa66d0000,0x241d221f,0xa6dd2764,0x2788a0a5,0xa16427a8,0x255fa7f6,0x25ed1a46,0x1648a6a7,0x27fea472,0xa73b1e3e,0x22d7a7d9,
0xa7c3262f,0x9fc6a513,0x9cb2270e,0xa7ea238b,0xa5ed2800,0xa55f0000,0xa7882764,0xa164a21f,0x24c41a46,0xa66d27f6,0x1fc6238b,0xa7c3270e,
0x26dda7d9,0x241d1e3e,0x27eaa6a7,0x1cb22472,0xa2d7a0a5,0x273ba7a8,0x9648a513,0x27fea62f,0xa6dd2800,0xa41d0000,0x9cb2a21f,0x27eaa764,
0x1648238b,0xa7fe270e,0xa7882513,0x2164a62f,0x273ba472,0xa2d726a7,0xa5ed27d9,0xa55f1e3e,0x266da7f6,0x24c49a46,0x1fc620a5,0xa7c327a8,
0xa7882800,0xa1640000,0x27fea764,0x9648221f,0xa41d262f,0xa6dd2513,0x266da7a8,0x24c4a0a5,0x1cb21e3e,0xa7ea27d9,0x1fc6a472,0x27c3a6a7,
0x25eda38b,0xa55f270e,0xa2d71a46,0x273ba7f6,0xa7ea2800,0x9cb20000,0x9fc6221f,0xa7c32764,0xa73b27a8,0xa2d720a5,0x16481a46,0xa7fe27f6,
0xa5ed26a7,0xa55f2472,0x21649e3e,0xa78827d9,0xa41d2513,0xa6dd262f,0x24c4a38b,0xa66d270e,0xa7fe2800,0x16480000,0xa73b2764,0x22d7a21f,
0xa7ea27f6,0x1cb29a46,0xa6dd270e,0x241da38b,0xa7c327d9,0x1fc69e3e,0xa66d26a7,0x24c4a472,0xa78827a8,0x2164a0a5,0xa5ed262f,0x255fa513,
0xa7c32800,0x1fc60000,0x24c4a21f,0x266da764,0xa5ed270e,0x255fa38b,0x273ba62f,0x22d7a513,0xa1642472,0x2788a6a7,0x27fea7d9,0x96489e3e,
0x1cb21a46,0x27eaa7f6,0x26dda7a8,0xa41d20a5,0xa73b2800,0x22d70000,0x255fa764,0xa5ed221f,0x9fc62513,0x27c3a62f,0x9cb2a0a5,0xa7ea27a8,
0x24c49e3e,0x266da7d9,0xa6dd2472,0xa41d26a7,0x27fea70e,0x1648a38b,0xa78827f6,0x21641a46,0xa66d2800,0x24c40000,0xa6dd221f,0xa41d2764,
0x216420a5,0x2788a7a8,0xa5ed27f6,0x255f9a46,0x27fea6a7,0x9648a472,0x22d71e3e,0x273ba7d9,0x1fc6a62f,0xa7c32513,0x27eaa70e,0x9cb2a38b,
0xa55f2800,0x25ed0000,0xa1642764,0x2788a21f,0x266d9a46,0x24c4a7f6,0x27c3a38b,0x1fc6a70e,0x241da7d9,0xa6dd1e3e,0x1cb2a6a7,0xa7ea2472,
0xa73b20a5,0xa2d727a8,0xa7fe2513,0x9648262f,0xa41d2800,0x26dd0000,0x27eaa21f,0x1cb2a764,0x27fea38b,0x1648a70e,0xa164a513,0xa788262f,
0xa2d7a472,0xa73b26a7,0xa55f27d9,0x25ed1e3e,0xa4c427f6,0x266d1a46,0x27c3a0a5,0x1fc6a7a8,0xa1642800,0x27880000,0x9648a764,0xa7fe221f,
0x26dda62f,0xa41da513,0xa4c427a8,0x266d20a5,0xa7ea1e3e,0x9cb227d9,0x27c3a472,0x9fc6a6a7,0x255f238b,0x25eda70e,0xa73b9a46,0xa2d727f6,
0x9cb22800,0x27ea0000,0xa7c3221f,0x1fc62764,0x22d7a7a8,0xa73ba0a5,0x27fe9a46,0x1648a7f6,0xa55f26a7,0x25ed2472,0xa7889e3e,0xa16427d9,
0x26dda513,0xa41da62f,0x266d238b,0x24c4a70e,0x16482800,0x27fe0000,0x22d72764,0x273ba21f,0x9cb2a7f6,0xa7ea1a46,0xa41da70e,0xa6dd238b,
0x1fc627d9,0x27c39e3e,0x24c426a7,0x266da472,0xa164a7a8,0xa78820a5,0xa55fa62f,0xa5ed2513,0x1fc62800,0x27c30000,0x266da21f,0xa4c4a764,
0xa55fa70e,0xa5ed238b,0xa2d7262f,0x273b2513,0x27882472,0x2164a6a7,0x9648a7d9,0xa7fe9e3e,0xa7ea9a46,0x1cb227f6,0x241d27a8,0x26dda0a5,
0x22d72800,0x273b0000,0xa5eda764,0xa55f221f,0xa7c3a513,0x9fc6262f,0x27ea20a5,0x9cb2a7a8,0x266d9e3e,0xa4c4a7d9,0xa41d2472,0x26dd26a7,
0x9648270e,0x27fe238b,0xa164a7f6,0xa7889a46,0x24c42800,0x266d0000,0xa41d221f,0x26dd2764,0xa788a0a5,0x216427a8,0xa55fa7f6,0xa5ed1a46,
0x9648a6a7,0xa7fea472,0x273b1e3e,0xa2d7a7d9,0x27c3262f,0x1fc6a513,0x1cb2270e,0x27ea238b,0x25ed2800,0x255f0000,0x27882764,0x2164a21f,
0xa4c41a46,0x266d27f6,0x9fc6238b,0x27c3270e,0xa6dda7d9,0xa41d1e3e,0xa7eaa6a7,0x9cb22472,0x22d7a0a5,0xa73ba7a8,0x1648a513,0xa7fea62f,
0x26dd2800,0x241d0000,0x1cb2a21f,0xa7eaa764,0x9648238b,0x27fe270e,0x27882513,0xa164a62f,0xa73ba472,0x22d726a7,0x25ed27d9,0x255f1e3e,
0xa66da7f6,0xa4c49a46,0x9fc620a5,0x27c327a8,0x27882800,0x21640000,0xa7fea764,0x1648221f,0x241d262f,0x26dd2513,0xa66da7a8,0xa4c4a0a5,
0x9cb21e3e,0x27ea27d9,0x9fc6a472,0xa7c3a6a7,0xa5eda38b,0x255f270e,0x22d71a46,0xa73ba7f6,0x27ea2800,0x1cb20000,0x1fc6221f,0x27c32764,
0x273b27a8,0x22d720a5,0x96481a46,0x27fe27f6,0x25ed26a7,0x255f2472,0xa1649e3e,0x278827d9,0x241d2513,0x26dd262f,0xa4c4a38b,0x266d270e,
0x255f25a8,0xa5eda5a8,0x2164221f,0xa788a764,0x24c42513,0xa66da62f,0x1fc620a5,0xa7c3a7a8,0x241d2472,0xa6dda6a7,0x1cb21e3e,0xa7eaa7d9,
0x22d7238b,0xa73ba70e,0x16481a46,0xa7fea7f6,0xa41da5a8,0x26dd25a8,0x27ea2764,0x1cb2221f,0x9648a0a5,0x27fe27a8,0x278827f6,0xa1649a46,
0x22d71e3e,0x273b27d9,0x255f26a7,0xa5eda472,0x266d2513,0x24c4262f,0x1fc6238b,0xa7c3a70e,0x216425a8,0xa788a5a8,0x1648a21f,0x27fe2764,
0xa41d9a46,0xa6dda7f6,0x266d238b,0x24c4270e,0xa7eaa6a7,0x9cb2a472,0x27c327d9,0x9fc61e3e,0xa5eda7a8,0x255f20a5,0x22d7262f,0xa73ba513,
0x9cb2a5a8,0x27ea25a8,0xa7c3a764,0x1fc6a21f,0x273b238b,0x22d7270e,0x9648a513,0x27fe262f,0x255f27d9,0xa5ed9e3e,0x27882472,0x216426a7,
0xa41d1a46,0xa6dda7f6,0x24c427a8,0xa66da0a5,0x964825a8,0xa7fea5a8,0xa2d7221f,0xa73ba764,0xa7eaa62f,0x1cb2a513,0xa6dda7a8,0x241da0a5,
0x1fc6a472,0x27c326a7,0x24c49e3e,0x266d27d9,0x2788270e,0xa164238b,0x25ed27f6,0xa55f1a46,0x1fc6a5a8,0x27c325a8,0x266d2764,0xa4c4221f,
0x25ed27a8,0xa55f20a5,0xa73b9a46,0xa2d7a7f6,0xa7889e3e,0xa164a7d9,0x1648a6a7,0x27fe2472,0x1cb2a62f,0x27ea2513,0x26dd270e,0xa41d238b,
0xa2d725a8,0xa73ba5a8,0x25eda21f,0x255f2764,0x9fc6a7f6,0x27c31a46,0x9cb2270e,0xa7eaa38b,0x266d26a7,0xa4c42472,0xa41da7d9,0x26dd9e3e,
0xa7fea0a5,0x9648a7a8,0x27882513,0xa164262f,0x24c4a5a8,0x266d25a8,0xa41da764,0x26dda21f,0xa164270e,0xa788a38b,0x25ed262f,0xa55f2513,
0x1648a7d9,0x27fe1e3e,0xa73ba472,0x22d7a6a7,0x1fc627f6,0xa7c31a46,0x27ea20a5,0x9cb227a8,0xa5ed25a8,0xa55fa5a8,0xa788221f,0xa164a764,
0x266da513,0x24c4262f,0x27c3a0a5,0x1fc627a8,0xa6dd2472,0xa41da6a7,0xa7ea1e3e,0x9cb2a7d9,0x273ba38b,0x22d7270e,0x27fe9a46,0x164827f6,
0x26dda5a8,0x241d25a8,0x1cb22764,0xa7ea221f,0xa7fe20a5,0x9648a7a8,0x2164a7f6,0x27881a46,0x273b1e3e,0xa2d727d9,0xa5ed26a7,0xa55fa472,
0xa4c4a513,0x266da62f,0x27c3a38b,0x1fc6270e,0xa78825a8,0xa164a5a8,0x27fea21f,0x96482764,0x26dd1a46,0xa41d27f6,0xa4c4a38b,0x266da70e,
0x9cb2a6a7,0x27eaa472,0x9fc627d9,0xa7c31e3e,0xa55f27a8,0xa5eda0a5,0x273ba62f,0x22d72513,0x27eaa5a8,0x1cb225a8,0x1fc6a764,0x27c3a21f,
0xa2d7a38b,0x273ba70e,0xa7fe2513,0x9648a62f,0xa5ed27d9,0xa55f9e3e,0x21642472,0xa78826a7,0x26dd9a46,0xa41d27f6,0x266da7a8,0x24c420a5,
0xa7fe25a8,0x1648a5a8,0xa73b221f,0x22d7a764,0x9cb2262f,0xa7ea2513,0xa41d27a8,0xa6dd20a5,0x27c3a472,0x9fc626a7,0x266d9e3e,0xa4c427d9,
0x2164a70e,0x2788a38b,0x255fa7f6,0x25ed9a46,0x27c3a5a8,0x9fc625a8,0xa4c42764,0xa66d221f,0x255fa7a8,0x25eda0a5,0x22d71a46,0xa73b27f6,
0xa1649e3e,0x2788a7d9,0x27fea6a7,0x96482472,0xa7ea262f,0x1cb2a513,0x241da70e,0x26dda38b,0xa73b25a8,0x22d7a5a8,0x255fa21f,0xa5ed2764,
0xa7c327f6,0x9fc69a46,0x27eaa70e,0x9cb2238b,0xa4c426a7,0xa66d2472,0x26dda7d9,0x241d9e3e,0x164820a5,0xa7fe27a8,0x2164a513,0x2788a62f,
0x266da5a8,0xa4c425a8,0x26dda764,0x241da21f,0x2788a70e,0xa164238b,0x255fa62f,0x25eda513,0x27fea7d9,0x96481e3e,0x22d7a472,0x273ba6a7,
0x27c3a7f6,0x1fc69a46,0x1cb2a0a5,0x27eaa7a8,0xa55f25a8,0x25eda5a8,0xa164221f,0x2788a764,0xa4c42513,0x266da62f,0x9fc620a5,0x27c3a7a8,
0xa41d2472,0x26dda6a7,0x9cb21e3e,0x27eaa7d9,0xa2d7238b,0x273ba70e,0x96481a46,0x27fea7f6,0x241da5a8,0xa6dd25a8,0xa7ea2764,0x9cb2221f,
0x1648a0a5,0xa7fe27a8,0xa78827f6,0x21649a46,0xa2d71e3e,0xa73b27d9,0xa55f26a7,0x25eda472,0xa66d2513,0xa4c4262f,0x9fc6238b,0x27c3a70e,
0xa16425a8,0x2788a5a8,0x9648a21f,0xa7fe2764,0x241d9a46,0x26dda7f6,0xa66d238b,0xa4c4270e,0x27eaa6a7,0x1cb2a472,0xa7c327d9,0x1fc61e3e,
0x25eda7a8,0xa55f20a5,0xa2d7262f,0x273ba513,0x1cb2a5a8,0xa7ea25a8,0x27c3a764,0x9fc6a21f,0xa73b238b,0xa2d7270e,0x1648a513,0xa7fe262f,
0xa55f27d9,0x25ed9e3e,0xa7882472,0xa16426a7,0x241d1a46,0x26dda7f6,0xa4c427a8,0x266da0a5,0x164825a8,0x27fea5a8,0x22d7221f,0x273ba764,
0x27eaa62f,0x9cb2a513,0x26dda7a8,0xa41da0a5,0x9fc6a472,0xa7c326a7,0xa4c49e3e,0xa66d27d9,0xa788270e,0x2164238b,0xa5ed27f6,0x255f1a46,
0x9fc6a5a8,0xa7c325a8,0xa66d2764,0x24c4221f,0xa5ed27a8,0x255f20a5,0x273b9a46,0x22d7a7f6,0x27889e3e,0x2164a7d9,0x9648a6a7,0xa7fe2472,
0x9cb2a62f,0xa7ea2513,0xa6dd270e,0x241d238b,0x22d725a8,0x273ba5a8,0xa5eda21f,0xa55f2764,0x1fc6a7f6,0xa7c31a46,0x1cb2270e,0x27eaa38b,
0xa66d26a7,0x24c42472,0x241da7d9,0xa6dd9e3e,0x27fea0a5,0x1648a7a8,0xa7882513,0x2164262f,0xa4c4a5a8,0xa66d25a8,0x241da764,0xa6dda21f,
0x2164270e,0x2788a38b,0xa5ed262f,0x255f2513,0x9648a7d9,0xa7fe1e3e,0x273ba472,0xa2d7a6a7,0x9fc627f6,0x27c31a46,0xa7ea20a5,0x1cb227a8,
0x25ed25a8,0x255fa5a8,0x2788221f,0x2164a764,0xa66da513,0xa4c4262f,0xa7c3a0a5,0x9fc627a8,0x26dd2472,0x241da6a7,0x27ea1e3e,0x1cb2a7d9,
0xa73ba38b,0xa2d7270e,0xa7fe9a46,0x964827f6,0xa6dda5a8,0xa41d25a8,0x9cb22764,0x27ea221f,0x27fe20a5,0x1648a7a8,0xa164a7f6,0xa7881a46,
0xa73b1e3e,0x22d727d9,0x25ed26a7,0x255fa472,0x24c4a513,0xa66da62f,0xa7c3a38b,0x9fc6270e,0x278825a8,0x2164a5a8,0xa7fea21f,0x16482764,
0xa6dd1a46,0x241d27f6,0x24c4a38b,0xa66da70e,0x1cb2a6a7,0xa7eaa472,0x1fc627d9,0x27c31e3e,0x255f27a8,0x25eda0a5,0xa73ba62f,0xa2d72513,
0xa7eaa5a8,0x9cb225a8,0x9fc6a764,0xa7c3a21f,0x22d7a38b,0xa73ba70e,0x27fe2513,0x1648a62f,0x25ed27d9,0x255f9e3e,0xa1642472,0x278826a7,
0xa6dd9a46,0x241d27f6,0xa66da7a8,0xa4c420a5,0x27fe25a8,0x9648a5a8,0x273b221f,0xa2d7a764,0x1cb2262f,0x27ea2513,0x241d27a8,0x26dd20a5,
0xa7c3a472,0x1fc626a7,0xa66d9e3e,0x24c427d9,0xa164a70e,0xa788a38b,0xa55fa7f6,0xa5ed9a46,0xa7c3a5a8,0x1fc625a8,0x24c42764,0x266d221f,
0xa55fa7a8,0xa5eda0a5,0xa2d71a46,0x273b27f6,0x21649e3e,0xa788a7d9,0xa7fea6a7,0x16482472,0x27ea262f,0x9cb2a513,0xa41da70e,0xa6dda38b,
0x273b25a8,0xa2d7a5a8,0xa55fa21f,0x25ed2764,0x27c327f6,0x1fc69a46,0xa7eaa70e,0x1cb2238b,0x24c426a7,0x266d2472,0xa6dda7d9,0xa41d9e3e,
0x964820a5,0x27fe27a8,0xa164a513,0xa788a62f,0xa66da5a8,0x24c425a8,0xa6dda764,0xa41da21f,0xa788a70e,0x2164238b,0xa55fa62f,0xa5eda513,
0xa7fea7d9,0x16481e3e,0xa2d7a472,0xa73ba6a7,0xa7c3a7f6,0x9fc69a46,0x9cb2a0a5,0xa7eaa7a8,
};

#define PROF(slot) do {} while (0)
#define PROF3(slot) do {} while (0)
#define PROF2(slot) do {} while (0)

__device__ __forceinline__ uint32_t smem_u32(const void* p) { return (uint32_t)__cvta_generic_to_shared(p); }

__device__ __forceinline__ void mbar_init(uint32_t a, uint32_t c) {
  asm volatile("mbarrier.init.shared::cta.b64 [%0], %1;\n" ::"r"(a), "r"(c) : "memory");
}
__device__ __forceinline__ void mbar_expect_tx(uint32_t a, uint32_t bytes) {
  asm volatile("mbarrier.arrive.expect_tx.shared::cta.b64 _, [%0], %1;\n" ::"r"(a), "r"(bytes) : "memory");
}
__device__ __forceinline__ void mbar_arrive_cluster(uint32_t cluster_addr) {
  asm volatile("mbarrier.arrive.shared::cluster.b64 _, [%0];\n" ::"r"(cluster_addr) : "memory");
}
__device__ __forceinline__ void mbar_arrive_cluster_n(uint32_t cluster_addr, uint32_t n) {
  asm volatile("mbarrier.arrive.shared::cluster.b64 _, [%0], %1;\n" ::"r"(cluster_addr), "r"(n) : "memory");
}
__device__ __forceinline__ bool mbar_try(uint32_t a, uint32_t parity) {
  uint32_t ok;
  asm volatile("{\n.reg .pred p;\nmbarrier.try_wait.parity.shared::cta.b64 p, [%1], %2;\nselp.u32 %0, 1, 0, p;\n}\n"
               : "=r"(ok) : "r"(a), "r"(parity) : "memory");
  return ok;
}
__device__ __forceinline__ void mbar_wait(uint32_t a, uint32_t parity) {
  if (mbar_try(a, parity)) return;
#pragma unroll 1
  for (int n = 0; n < SPIN_LIMIT; n++)
    if (mbar_try(a, parity)) break;
}
__device__ __forceinline__ void mbar_wait_idle(uint32_t a, uint32_t parity) {
#pragma unroll 1
  for (int n = 0; n < SPIN_LIMIT; n++) {
    uint32_t ok;
    asm volatile("{\n.reg .pred p;\nmbarrier.try_wait.parity.shared::cta.b64 p, [%1], %2, %3;\nselp.u32 %0, 1, 0, p;\n}\n"
                 : "=r"(ok) : "r"(a), "r"(parity), "r"(4000) : "memory");
    if (ok) break;
  }
}
__device__ __forceinline__ bool elect_one() {
  uint32_t p;
  asm volatile("{\n.reg .pred P;\nelect.sync _|P, 0xffffffff;\nselp.u32 %0, 1, 0, P;\n}\n" : "=r"(p));
  return p;
}
__device__ __forceinline__ uint32_t mapa(uint32_t a, uint32_t rank) {
  uint32_t r;
  asm volatile("mapa.shared::cluster.u32 %0, %1, %2;\n" : "=r"(r) : "r"(a), "r"(rank));
  return r;
}
__device__ __forceinline__ void nb_sync(int id, int n) { asm volatile("bar.sync %0, %1;\n" ::"r"(id), "r"(n) : "memory"); }
__device__ __forceinline__ void nb_arrive(int id, int n) { asm volatile("bar.arrive %0, %1;\n" ::"r"(id), "r"(n) : "memory"); }
__device__ __forceinline__ void cluster_sync_all() {
  asm volatile("barrier.cluster.arrive.relaxed.aligned;\nbarrier.cluster.wait.aligned;\n" ::: "memory");
}
__device__ __forceinline__ void fence_async_smem() { asm volatile("fence.proxy.async.shared::cta;\n" ::: "memory"); }
__device__ __forceinline__ void fence_async_all() { asm volatile("fence.proxy.async.global;\n" ::: "memory"); }

__device__ __forceinline__ void tma_load_3d(uint32_t dst, const CUtensorMap* tm, uint32_t bar, int c0, int c1, int c2) {
  asm volatile(
      "cp.async.bulk.tensor.3d.shared::cluster.global.mbarrier::complete_tx::bytes [%0], [%1, {%3, %4, %5}], [%2];\n"
      ::"r"(dst), "l"(tm), "r"(bar), "r"(c0), "r"(c1), "r"(c2) : "memory");
}
__device__ __forceinline__ void tma_load_4d(uint32_t dst, const CUtensorMap* tm, uint32_t bar, int c0, int c1, int c2, int c3) {
  asm volatile(
      "cp.async.bulk.tensor.4d.shared::cluster.global.mbarrier::complete_tx::bytes [%0], [%1, {%3, %4, %5, %6}], [%2];\n"
      ::"r"(dst), "l"(tm), "r"(bar), "r"(c0), "r"(c1), "r"(c2), "r"(c3) : "memory");
}
__device__ __forceinline__ void tma_load_3d_mc(uint32_t dst, const CUtensorMap* tm, uint32_t bar, int c0, int c1, int c2) {
  asm volatile(
      "cp.async.bulk.tensor.3d.shared::cluster.global.mbarrier::complete_tx::bytes.multicast::cluster [%0], [%1, {%3, %4, %5}], [%2], %6;\n"
      ::"r"(dst), "l"(tm), "r"(bar), "r"(c0), "r"(c1), "r"(c2), "h"((uint16_t)3) : "memory");
}
__device__ __forceinline__ void tma_load_5d(uint32_t dst, const CUtensorMap* tm, uint32_t bar, int c0, int c4) {
  asm volatile(
      "cp.async.bulk.tensor.5d.shared::cluster.global.mbarrier::complete_tx::bytes [%0], [%1, {%3, %5, %5, %5, %4}], [%2];\n"
      ::"r"(dst), "l"(tm), "r"(bar), "r"(c0), "r"(c4), "r"(0) : "memory");
}
__device__ __forceinline__ void bulk_load(uint32_t dst, const void* src, uint32_t bytes, uint32_t bar) {
  asm volatile("cp.async.bulk.shared::cluster.global.mbarrier::complete_tx::bytes [%0], [%1], %2, [%3];\n"
               ::"r"(dst), "l"(src), "r"(bytes), "r"(bar) : "memory");
}
__device__ __forceinline__ void bulk_commit() { asm volatile("cp.async.bulk.commit_group;\n" ::: "memory"); }
__device__ __forceinline__ void bulk_wait0() { asm volatile("cp.async.bulk.wait_group 0;\n" ::: "memory"); }
__device__ __forceinline__ void prefetch_tmap(const CUtensorMap* tm) {
  asm volatile("prefetch.tensormap [%0];\n" ::"l"(tm) : "memory");
}

__device__ __forceinline__ void wg_fence() { asm volatile("wgmma.fence.sync.aligned;\n" ::: "memory"); }
__device__ __forceinline__ void wg_commit() { asm volatile("wgmma.commit_group.sync.aligned;\n" ::: "memory"); }
template <int N> __device__ __forceinline__ void wg_wait() {
  asm volatile("wgmma.wait_group.sync.aligned %0;\n" ::"n"(N) : "memory");
}
__device__ __forceinline__ uint64_t mkdesc(uint32_t addr, uint32_t lbo, uint32_t sbo, uint32_t swz) {
  return (uint64_t)((addr & 0x3FFFF) >> 4) | ((uint64_t)(lbo >> 4) << 16) | ((uint64_t)(sbo >> 4) << 32) |
         ((uint64_t)swz << 62);
}

#define R4(d, o) "+f"(d[o + 0]), "+f"(d[o + 1]), "+f"(d[o + 2]), "+f"(d[o + 3])
#define R8(d, o) R4(d, o), R4(d, o + 4)
#define R16(d, o) R8(d, o), R8(d, o + 8)
#define R32(d, o) R16(d, o), R16(d, o + 16)
#define R64(d, o) R32(d, o), R32(d, o + 32)

__device__ __forceinline__ void wgmma_n192(float (&d)[96], uint64_t da, uint64_t db, uint32_t acc) {
  asm volatile(
      "{\n.reg .pred p;\nsetp.ne.u32 p, %98, 0;\n"
      "wgmma.mma_async.sync.aligned.m64n192k16.f32.bf16.bf16 "
      "{%0,%1,%2,%3,%4,%5,%6,%7,%8,%9,%10,%11,%12,%13,%14,%15,%16,%17,%18,%19,%20,%21,%22,%23,%24,%25,%26,%27,%28,%29,%30,%31,"
      "%32,%33,%34,%35,%36,%37,%38,%39,%40,%41,%42,%43,%44,%45,%46,%47,%48,%49,%50,%51,%52,%53,%54,%55,%56,%57,%58,%59,%60,%61,%62,%63,"
      "%64,%65,%66,%67,%68,%69,%70,%71,%72,%73,%74,%75,%76,%77,%78,%79,%80,%81,%82,%83,%84,%85,%86,%87,%88,%89,%90,%91,%92,%93,%94,%95}, "
      "%96, %97, p, 1, 1, 0, 1;\n}\n"
      : R64(d, 0), R32(d, 64)
      : "l"(da), "l"(db), "r"(acc));
}
__device__ __forceinline__ void wgmma_n128(float (&d)[64], uint64_t da, uint64_t db, uint32_t acc) {
  asm volatile(
      "{\n.reg .pred p;\nsetp.ne.u32 p, %66, 0;\n"
      "wgmma.mma_async.sync.aligned.m64n128k16.f32.bf16.bf16 "
      "{%0,%1,%2,%3,%4,%5,%6,%7,%8,%9,%10,%11,%12,%13,%14,%15,%16,%17,%18,%19,%20,%21,%22,%23,%24,%25,%26,%27,%28,%29,%30,%31,"
      "%32,%33,%34,%35,%36,%37,%38,%39,%40,%41,%42,%43,%44,%45,%46,%47,%48,%49,%50,%51,%52,%53,%54,%55,%56,%57,%58,%59,%60,%61,%62,%63}, "
      "%64, %65, p, 1, 1, 0, 1;\n}\n"
      : R64(d, 0)
      : "l"(da), "l"(db), "r"(acc));
}
template <int N> __device__ __forceinline__ void fence_regs(float (&d)[N]) {
#pragma unroll
  for (int i = 0; i < N; i++) asm volatile("" : "+f"(d[i])::"memory");
}

__device__ __forceinline__ void mma16816(float (&d)[4], uint32_t a0, uint32_t a1, uint32_t a2, uint32_t a3, uint32_t b0,
                                         uint32_t b1) {
  asm("mma.sync.aligned.m16n8k16.row.col.f32.bf16.bf16.f32 {%0,%1,%2,%3}, {%4,%5,%6,%7}, {%8,%9}, {%0,%1,%2,%3};\n"
      : "+f"(d[0]), "+f"(d[1]), "+f"(d[2]), "+f"(d[3])
      : "r"(a0), "r"(a1), "r"(a2), "r"(a3), "r"(b0), "r"(b1));
}
__device__ __forceinline__ void mma16816_z(float (&d)[4], uint32_t a0, uint32_t a1, uint32_t a2, uint32_t a3, uint32_t b0,
                                           uint32_t b1) {
  asm("mma.sync.aligned.m16n8k16.row.col.f32.bf16.bf16.f32 {%0,%1,%2,%3}, {%4,%5,%6,%7}, {%8,%9}, {%10,%10,%10,%10};\n"
      : "=f"(d[0]), "=f"(d[1]), "=f"(d[2]), "=f"(d[3])
      : "r"(a0), "r"(a1), "r"(a2), "r"(a3), "r"(b0), "r"(b1), "f"(0.f));
}
__device__ __forceinline__ void ldsm4t(uint32_t (&r)[4], uint32_t a) {
  asm volatile("ldmatrix.sync.aligned.m8n8.x4.trans.shared.b16 {%0,%1,%2,%3}, [%4];\n"
               : "=r"(r[0]), "=r"(r[1]), "=r"(r[2]), "=r"(r[3]) : "r"(a) : "memory");
}
__device__ __forceinline__ void ldsm2t(uint32_t& r0, uint32_t& r1, uint32_t a) {
  asm volatile("ldmatrix.sync.aligned.m8n8.x2.trans.shared.b16 {%0,%1}, [%2];\n" : "=r"(r0), "=r"(r1) : "r"(a) : "memory");
}
__device__ __forceinline__ void st_async128(uint32_t a, uint32_t bar, uint32_t x, uint32_t y, uint32_t z, uint32_t w) {
  asm volatile("st.async.weak.shared::cluster.mbarrier::complete_tx::bytes.v4.b32 [%0], {%2,%3,%4,%5}, [%1];\n"
               ::"r"(a), "r"(bar), "r"(x), "r"(y), "r"(z), "r"(w) : "memory");
}
__device__ __forceinline__ void mbar_arrive(uint32_t a) {
  asm volatile("mbarrier.arrive.shared::cta.b64 _, [%0];\n" ::"r"(a) : "memory");
}
__device__ __forceinline__ void stsm4(uint32_t a, uint32_t r0, uint32_t r1, uint32_t r2, uint32_t r3) {
  asm volatile("stmatrix.sync.aligned.m8n8.x4.shared.b16 [%0], {%1,%2,%3,%4};\n"
               ::"r"(a), "r"(r0), "r"(r1), "r"(r2), "r"(r3) : "memory");
}
__device__ __forceinline__ void stsm4t(uint32_t a, uint32_t r0, uint32_t r1, uint32_t r2, uint32_t r3) {
  asm volatile("stmatrix.sync.aligned.m8n8.x4.trans.shared.b16 [%0], {%1,%2,%3,%4};\n"
               ::"r"(a), "r"(r0), "r"(r1), "r"(r2), "r"(r3) : "memory");
}
__device__ __forceinline__ uint2 lds64(uint32_t a) {
  uint2 v;
  asm volatile("ld.shared.v2.u32 {%0,%1}, [%2];\n" : "=r"(v.x), "=r"(v.y) : "r"(a));
  return v;
}
__device__ __forceinline__ uint4 lds128(uint32_t a) {
  uint4 v;
  asm volatile("ld.shared.v4.u32 {%0,%1,%2,%3}, [%4];\n" : "=r"(v.x), "=r"(v.y), "=r"(v.z), "=r"(v.w) : "r"(a) : "memory");
  return v;
}
__device__ __forceinline__ void sts128(uint32_t a, uint32_t x, uint32_t y, uint32_t z, uint32_t w) {
  asm volatile("st.shared.v4.u32 [%0], {%1,%2,%3,%4};\n" ::"r"(a), "r"(x), "r"(y), "r"(z), "r"(w) : "memory");
}
__device__ __forceinline__ uint32_t pack_bf16(float lo, float hi) {
  uint32_t r;
  asm("cvt.rn.bf16x2.f32 %0, %1, %2;\n" : "=r"(r) : "f"(hi), "f"(lo));
  return r;
}
__device__ __forceinline__ uint32_t bmul2(uint32_t a, uint32_t b) {
  uint32_t r;
  asm("mul.rn.bf16x2 %0, %1, %2;\n" : "=r"(r) : "r"(a), "r"(b));
  return r;
}
__device__ __forceinline__ uint32_t bmax2(uint32_t a, uint32_t b) {
  uint32_t r;
  asm("max.bf16x2 %0, %1, %2;\n" : "=r"(r) : "r"(a), "r"(b));
  return r;
}
__device__ __forceinline__ uint32_t bfma2(uint32_t a, uint32_t b, uint32_t c) {
  uint32_t r;
  asm("fma.rn.bf16x2 %0, %1, %2, %3;\n" : "=r"(r) : "r"(a), "r"(b), "r"(c));
  return r;
}
__device__ __forceinline__ uint32_t badd2(uint32_t a, uint32_t b) {
  uint32_t r;
  asm("add.rn.bf16x2 %0, %1, %2;\n" : "=r"(r) : "r"(a), "r"(b));
  return r;
}
__device__ __forceinline__ void prefetch_l2(const void* p) { asm volatile("prefetch.global.L2 [%0];\n" ::"l"(p)); }
__device__ __forceinline__ void cp_async16n(uint32_t dst, const void* src) {
  asm volatile("cp.async.cg.shared.global [%0], [%1], 16;\n" ::"r"(dst), "l"(src) : "memory");
}
__device__ __forceinline__ void cp_async16(uint32_t dst, const void* src, uint32_t srcbytes) {
  asm volatile("cp.async.cg.shared.global.L2::256B [%0], [%1], 16, %2;\n" ::"r"(dst), "l"(src), "r"(srcbytes) : "memory");
}
__device__ __forceinline__ uint32_t ld_acquire(const uint32_t* p) {
  uint32_t v;
  asm volatile("ld.acquire.gpu.global.u32 %0, [%1];\n" : "=r"(v) : "l"(p) : "memory");
  return v;
}
__device__ __forceinline__ uint32_t ld_relaxed(const uint32_t* p) {
  uint32_t v;
  asm volatile("ld.relaxed.gpu.global.u32 %0, [%1];\n" : "=r"(v) : "l"(p) : "memory");
  return v;
}
__device__ __forceinline__ void st_release(uint32_t* p, uint32_t v) {
  asm volatile("st.release.gpu.global.u32 [%0], %1;\n" ::"l"(p), "r"(v) : "memory");
}
__device__ __forceinline__ void wait_flag(const uint32_t* p, uint32_t want) {
  int n = 0;
  while (ld_relaxed(p) != want && ++n < SPIN_LIMIT) __nanosleep(40);
  (void)ld_acquire(p);
}

struct Params {
  const __nv_bfloat16* x;
  const __nv_bfloat16* w;
  const __nv_bfloat16* q;
  const __nv_bfloat16* k;
  const __nv_bfloat16* v;
  const __nv_bfloat16* shift_k;
  const __nv_bfloat16* ssm_k;
  const __nv_bfloat16* ssm_D;
  const __nv_bfloat16* wo;
  __nv_bfloat16* out;
};

__device__ __forceinline__ uint32_t lds32(uint32_t a) {
  uint32_t v;
  asm volatile("ld.shared.u32 %0, [%1];\n" : "=r"(v) : "r"(a));
  return v;
}
#define W4(d, o) "=f"(d[o + 0]), "=f"(d[o + 1]), "=f"(d[o + 2]), "=f"(d[o + 3])
#define W8(d, o) W4(d, o), W4(d, o + 4)
#define W16(d, o) W8(d, o), W8(d, o + 8)
#define U4(c, d, o) c(d[o + 0]), c(d[o + 1]), c(d[o + 2]), c(d[o + 3])
#define U8(c, d, o) U4(c, d, o), U4(c, d, o + 4)
#define U16(c, d, o) U8(c, d, o), U8(c, d, o + 8)
#define U32(c, d, o) U16(c, d, o), U16(c, d, o + 16)
#define D32 "{%0,%1,%2,%3,%4,%5,%6,%7,%8,%9,%10,%11,%12,%13,%14,%15,%16,%17,%18,%19,%20,%21,%22,%23,%24,%25,%26,%27,%28,%29,%30,%31}"
#define D16 "{%0,%1,%2,%3,%4,%5,%6,%7,%8,%9,%10,%11,%12,%13,%14,%15}"
#define D8 "{%0,%1,%2,%3,%4,%5,%6,%7}"
template <int ACC> __device__ __forceinline__ void hmma_n128t(uint32_t (&d)[32], const uint32_t (&a)[4], uint64_t db) {
  if (ACC)
    asm volatile("wgmma.mma_async.sync.aligned.m64n128k16.f16.f16.f16 " D32 ", {%32,%33,%34,%35}, %36, 1, 1, 1, 1;\n"
                 : U32("+r", d, 0) : "r"(a[0]), "r"(a[1]), "r"(a[2]), "r"(a[3]), "l"(db));
  else
    asm volatile("wgmma.mma_async.sync.aligned.m64n128k16.f16.f16.f16 " D32 ", {%32,%33,%34,%35}, %36, 0, 1, 1, 1;\n"
                 : U32("=r", d, 0) : "r"(a[0]), "r"(a[1]), "r"(a[2]), "r"(a[3]), "l"(db));
}
template <int ACC, int TB> __device__ __forceinline__ void hmma_n32(uint32_t (&d)[8], const uint32_t (&a)[4], uint64_t db) {
  if (ACC)
    asm volatile("wgmma.mma_async.sync.aligned.m64n32k16.f16.f16.f16 " D8 ", {%8,%9,%10,%11}, %12, 1, 1, 1, %13;\n"
                 : U8("+r", d, 0) : "r"(a[0]), "r"(a[1]), "r"(a[2]), "r"(a[3]), "l"(db), "n"(TB));
  else
    asm volatile("wgmma.mma_async.sync.aligned.m64n32k16.f16.f16.f16 " D8 ", {%8,%9,%10,%11}, %12, 0, 1, 1, %13;\n"
                 : U8("=r", d, 0) : "r"(a[0]), "r"(a[1]), "r"(a[2]), "r"(a[3]), "l"(db), "n"(TB));
}
template <int ACC> __device__ __forceinline__ void hmma_n64t(uint32_t (&d)[16], const uint32_t (&a)[4], uint64_t db) {
  if (ACC)
    asm volatile("wgmma.mma_async.sync.aligned.m64n64k16.f16.f16.f16 " D16 ", {%16,%17,%18,%19}, %20, 1, 1, 1, 1;\n"
                 : U16("+r", d, 0) : "r"(a[0]), "r"(a[1]), "r"(a[2]), "r"(a[3]), "l"(db));
  else
    asm volatile("wgmma.mma_async.sync.aligned.m64n64k16.f16.f16.f16 " D16 ", {%16,%17,%18,%19}, %20, 0, 1, 1, 1;\n"
                 : U16("=r", d, 0) : "r"(a[0]), "r"(a[1]), "r"(a[2]), "r"(a[3]), "l"(db));
}
template <int N> __device__ __forceinline__ void fence_regs(uint32_t (&d)[N]) {
#pragma unroll
  for (int i = 0; i < N; i++) asm volatile("" : "+r"(d[i])::"memory");
}
__device__ __forceinline__ uint32_t hmul(uint32_t a, uint32_t b) { uint32_t r; asm("mul.rn.f16x2 %0, %1, %2;\n" : "=r"(r) : "r"(a), "r"(b)); return r; }
__device__ __forceinline__ uint32_t hadd(uint32_t a, uint32_t b) { uint32_t r; asm("add.rn.f16x2 %0, %1, %2;\n" : "=r"(r) : "r"(a), "r"(b)); return r; }
__device__ __forceinline__ uint32_t hsub(uint32_t a, uint32_t b) { uint32_t r; asm("sub.rn.f16x2 %0, %1, %2;\n" : "=r"(r) : "r"(a), "r"(b)); return r; }
__device__ __forceinline__ uint32_t hfma(uint32_t a, uint32_t b, uint32_t c) { uint32_t r; asm("fma.rn.f16x2 %0, %1, %2, %3;\n" : "=r"(r) : "r"(a), "r"(b), "r"(c)); return r; }
__device__ __forceinline__ uint32_t hfnma(uint32_t a, uint32_t b, uint32_t c) {
  uint32_t r;
  asm("{\n.reg .b32 t;\nneg.f16x2 t, %1;\nfma.rn.f16x2 %0, t, %2, %3;\n}\n" : "=r"(r) : "r"(a), "r"(b), "r"(c));
  return r;
}
__device__ __forceinline__ uint32_t hrefl(uint32_t p, uint32_t s) {
  uint32_t r;
  asm("{\n.reg .b32 t;\nneg.f16x2 t, %2;\nfma.rn.f16x2 %0, %1, %3, t;\n}\n" : "=r"(r) : "r"(p), "r"(s), "r"(0x40004000u));
  return r;
}
__device__ __forceinline__ void bfly(uint32_t xr, uint32_t xi, uint32_t tr, uint32_t ti, uint32_t yr, uint32_t yi, uint32_t ur,
                                     uint32_t ui, uint32_t& sr, uint32_t& si, uint32_t& dr, uint32_t& di) {
  const uint32_t pr = hfnma(xi, ti, hmul(xr, tr)), pi = hfma(xi, tr, hmul(xr, ti));
  sr = hfnma(yi, ui, hfma(yr, ur, pr));
  si = hfma(yi, ur, hfma(yr, ui, pi));
  dr = hrefl(pr, sr);
  di = hrefl(pi, si);
}
template <int BH> __device__ __forceinline__ void fft_e1(const uint32_t (&d)[32], const uint32_t (&tw)[16], uint32_t (&a2)[2][2][4]) {
#pragma unroll
  for (int be = 0; be < 2; be++)
#pragma unroll
    for (int s = 0; s < 2; s++) {
      const int o = 16 * s + 8 * be + 2 * BH, p = 2 * BH;
      bfly(d[o], d[o + 1], tw[p], tw[p + 1], d[o + 4], d[o + 5], tw[p + 4], tw[p + 5], a2[be][0][s], a2[be][0][2 + s],
           a2[be][1][s], a2[be][1][2 + s]);
    }
}
__device__ __forceinline__ uint32_t hfms(uint32_t a, uint32_t b, uint32_t c) {
  uint32_t r;
  asm("{\n.reg .b32 t;\nneg.f16x2 t, %3;\nfma.rn.f16x2 %0, %1, %2, t;\n}\n" : "=r"(r) : "r"(a), "r"(b), "r"(c));
  return r;
}
template <int C, int J> __device__ __forceinline__ void fft_e2(const uint32_t (&d0)[8], const uint32_t (&d1)[8], uint32_t (&a3)[2][4]) {
  const uint32_t ur = d0[2 * J], ui = d0[4 + 2 * J], hr = d0[2 * J + 1], hi = d0[5 + 2 * J];
  const uint32_t vr = d1[2 * J], vi = d1[4 + 2 * J], gr = d1[2 * J + 1], gi = d1[5 + 2 * J];
  const uint32_t pr = hfnma(ui, hi, hmul(ur, hr)), pi = hfma(ui, hr, hmul(ur, hi));
  a3[0][2 + C] = pr;
  a3[0][C] = pi;
  a3[1][2 + C] = hfnma(vi, hi, hfma(vr, hr, hfnma(ui, gi, hfms(ur, gr, pi))));
  a3[1][C] = hfma(vi, hr, hfma(vr, hi, hfma(ui, gr, hfma(ur, gi, pr))));
}
__device__ __forceinline__ void fft_e3(const uint32_t (&d)[2][8], const uint32_t (&tw)[16], uint32_t zaddr) {
#pragma unroll
  for (int rho = 0; rho < 2; rho++) {
    uint32_t zr[4], zi[4];
#pragma unroll
    for (int nb = 0; nb < 4; nb++) {
      const uint32_t xi = d[nb >> 1][2 * (nb & 1) + rho], xr = d[nb >> 1][4 + 2 * (nb & 1) + rho];
      const uint32_t tr = tw[8 + 4 * rho + 2 * (nb & 1)], ti = tw[9 + 4 * rho + 2 * (nb & 1)];
      zr[nb] = hfnma(xi, ti, hmul(xr, tr));
      zi[nb] = hfma(xi, tr, hmul(xr, ti));
    }
    stsm4(zaddr + rho * 2048, zr[0], zr[1], zr[2], zr[3]);
    stsm4(zaddr + rho * 2048 + 1024, zi[0], zi[1], zi[2], zi[3]);
  }
}
__device__ __forceinline__ float bf_lo(uint32_t v) {
  uint32_t r;
  asm("prmt.b32 %0, %1, 0, 0x1044;\n" : "=r"(r) : "r"(v));
  return __uint_as_float(r);
}
__device__ __forceinline__ float bf_hi(uint32_t v) { return __uint_as_float(v & 0xffff0000u); }
__device__ __forceinline__ float ex2(float x) {
  float r;
  asm("ex2.approx.ftz.f32 %0, %1;\n" : "=f"(r) : "f"(x));
  return r;
}
__device__ __forceinline__ float rcp(float x) {
  float r;
  asm("rcp.approx.ftz.f32 %0, %1;\n" : "=f"(r) : "f"(x));
  return r;
}

__device__ __forceinline__ int g2_a(int s, int h) { return (((0xA1023 ^ (h * 0x11)) >> (4 * s)) & 15) * 16384; }
__device__ __forceinline__ int g2_b(int s) { return ((0xCDB54 >> (4 * s)) & 15) * 16384; }
static_assert(OFF_U == 10 * 16384 && OFF_H == 12 * 16384 && OFF_OP == 2 * 16384, "units");
__device__ __forceinline__ int g2_k(int hp, int i) {
  return i < 2 ? hp ^ 1 ^ i : i < 4 ? (hp & ~1) ^ i : ((hp & ~3) + i) & 15; }
__device__ __forceinline__ int y_slot(int wg, int it) {
  static_assert(T_B2 == T_TW + 8192 && T_A1 == T_B2 + 4096, "y slots");
  return OFF_T + T_TW + ((it + 3) & 3) * 4096 + wg * 2048;
}

__device__ __forceinline__ void to_arr(uint32_t (&d)[4], uint4 v) { d[0] = v.x; d[1] = v.y; d[2] = v.z; d[3] = v.w; }

__device__ __forceinline__ void attn_stage(uint32_t sb, int blk, int lane, const float (&acc)[96], uint32_t (&k1)[2][4]) {
  const int lr = lane & 7, lm = lane >> 3;
  const uint32_t base = sb + OFF_VP + (blk * 16 + lr + 8 * (lm & 1)) * 128;
#pragma unroll
  for (int i = 0; i < 8; i++) k1[i >> 2][i & 3] = pack_bf16(acc[34 + 4 * i], acc[35 + 4 * i]);
  const uint32_t kh = sb + OFF_OP + (blk + 1) * 2048 + lane * 16;
  if (blk < 15) {
    sts128(kh, k1[0][0], k1[0][1], k1[0][2], k1[0][3]);
    sts128(kh + 512, k1[1][0], k1[1][1], k1[1][2], k1[1][3]);
  }
#pragma unroll
  for (int j = 0; j < 8; j += 2)
    stsm4(base + (((j + (lm >> 1)) ^ lr) << 4), pack_bf16(acc[64 + 4 * j], acc[65 + 4 * j]),
          pack_bf16(acc[66 + 4 * j], acc[67 + 4 * j]), pack_bf16(acc[68 + 4 * j], acc[69 + 4 * j]),
          pack_bf16(acc[70 + 4 * j], acc[71 + 4 * j]));
}
__device__ __forceinline__ void attn_pack(const float (&acc)[96], uint32_t (&qa)[2][8], uint32_t (&k0)[2][4]) {
#pragma unroll
  for (int hd = 0; hd < 2; hd++) {
#pragma unroll
    for (int i = 0; i < 8; i++) {
      asm volatile("cvt.rn.bf16x2.f32 %0, %1, %2;\n" : "=r"(qa[hd][i]) : "f"(acc[16 * hd + 2 * i + 1]), "f"(acc[16 * hd + 2 * i]));
    }
#pragma unroll
    for (int i = 0; i < 4; i++) {
      asm volatile("cvt.rn.bf16x2.f32 %0, %1, %2;\n" : "=r"(k0[hd][i]) : "f"(acc[33 + 16 * hd + 4 * i]), "f"(acc[32 + 16 * hd + 4 * i]));
    }
  }
}
__device__ __forceinline__ void attn_own(const uint32_t (&k0)[2][4], const uint32_t (&k1)[2][4], bool le0, bool le1,
                                         const uint32_t (&qa)[2][8], float (&l)[2][4]) {
#pragma unroll
  for (int hd = 0; hd < 2; hd++) {
    float s0[4], s1[4];
    mma16816_z(s0, qa[hd][0], qa[hd][1], qa[hd][2], qa[hd][3], k0[hd][0], k0[hd][1]);
    mma16816_z(s1, qa[hd][0], qa[hd][1], qa[hd][2], qa[hd][3], k1[hd][0], k1[hd][1]);
    mma16816(s0, qa[hd][4], qa[hd][5], qa[hd][6], qa[hd][7], k0[hd][2], k0[hd][3]);
    mma16816(s1, qa[hd][4], qa[hd][5], qa[hd][6], qa[hd][7], k1[hd][2], k1[hd][3]);
    l[hd][0] = s0[0];
    l[hd][1] = s0[1];
    l[hd][2] = le0 ? s1[2] : s0[2];
    l[hd][3] = le1 ? s1[3] : s0[3];
  }
}
template <int N> __device__ __forceinline__ void quad_softmax(float (&x)[N][2], uint32_t (&pp)[N]) {
  const float c2 = 1.4426950408889634f;
  uint32_t q[N], mx[N / 2];
#pragma unroll
  for (int n = 0; n < N; n++) {
    const uint32_t r = pack_bf16(x[n][0], x[n][1]);
    q[n] = bfma2(r, 0x3e353e35u, bmul2(r, 0x379e379eu));
    x[n][0] = bf_lo(q[n]);
    x[n][1] = bf_hi(q[n]);
  }
#pragma unroll
  for (int n = 0; n < N / 2; n++)
    mx[n] = bmax2(__byte_perm(q[2 * n], q[2 * n + 1], 0x5410), __byte_perm(q[2 * n], q[2 * n + 1], 0x7632));
#pragma unroll
  for (int o = 1; o <= 2; o++)
#pragma unroll
    for (int n = 0; n < N / 2; n++) mx[n] = bmax2(mx[n], __shfl_xor_sync(0xffffffffu, mx[n], o));
  float m[N], t[N];
#pragma unroll
  for (int n = 0; n < N / 2; n++) {
    m[2 * n] = bf_lo(mx[n]);
    m[2 * n + 1] = bf_hi(mx[n]);
  }
#pragma unroll
  for (int n = 0; n < N; n++) {
    const float nm = -m[n] * c2;
    x[n][0] = ex2(fmaf(x[n][0], c2, nm));
    x[n][1] = ex2(fmaf(x[n][1], c2, nm));
    t[n] = x[n][0] + x[n][1];
  }
#pragma unroll
  for (int o = 1; o <= 2; o++)
#pragma unroll
    for (int n = 0; n < N; n++) t[n] += __shfl_xor_sync(0xffffffffu, t[n], o);
#pragma unroll
  for (int n = 0; n < N; n++) {
    const float inv = rcp(t[n]);
    pp[n] = pack_bf16(x[n][0] * inv, x[n][1] * inv);
  }
}
__device__ __forceinline__ void attn_pv(uint32_t dst, const uint32_t (&va)[4], const uint32_t (&vb)[4], uint32_t pp,
                                        uint32_t maskLE) {
  const uint32_t b0 = pp & ~maskLE, b1 = pp & maskLE;
  float oa[4], ob[4];
  mma16816_z(oa, va[0], va[1], va[2], va[3], b0, b1);
  mma16816_z(ob, vb[0], vb[1], vb[2], vb[3], b0, b1);
  stsm4t(dst, pack_bf16(oa[0], oa[1]), pack_bf16(oa[2], oa[3]), pack_bf16(ob[0], ob[1]), pack_bf16(ob[2], ob[3]));
}

template <int MODE>
__global__ void __cluster_dims__(2, 1, 1) __launch_bounds__(NTHREADS, 1)
fused_kernel(const Params p, const __grid_constant__ CUtensorMap tmX, const __grid_constant__ CUtensorMap tmW,
             const __grid_constant__ CUtensorMap tmWo,
             const __grid_constant__ CUtensorMap tmQ,
             const __grid_constant__ CUtensorMap tmXh, const __grid_constant__ CUtensorMap tmWh) {
  extern __shared__ __align__(1024) uint8_t smem[];
  const uint32_t sb = smem_u32(smem) - OFF_L0;
  const uint32_t bars = sb + OFF_BAR;
  const int tid = threadIdx.x, lane = tid & 31, warp = __shfl_sync(0xffffffffu, tid >> 5, 0);
  const int rank = blockIdx.x & 1;
  const bool halo_cta = blockIdx.x < 4;
  if (halo_cta && MODE != 0) return;
  int grp, mem;
  {
    const int t = (blockIdx.x >> 1) - 4, u = t - 32;
    const int q7 = (u * 37) >> 8;
    const bool lo = (unsigned)t < 32u, mid = (unsigned)u < 28u;
    grp = lo ? (t & 7) : (mid ? 1 + u - 7 * q7 : 0);
    mem = lo ? (t >> 3) : (mid ? 4 + q7 : (t < 0 ? t + 6 : t - 54));
  }
  const int rg = (grp >> 2) * 4 + (mem >> 1), hp = (grp & 3) * 4 + (mem & 1) * 2 + rank;
  const int rb2 = (grp >> 2) * 8 + mem, cb2 = (grp & 3) * 2 + rank;
  const int chb = grp * 16 + mem * 2 + rank;
  const int cta = rg * 16 + hp;
  const int par = rg >> 2, gidx = rg & 3;

  if (tid < 256 && !halo_cta && MODE != 2) {
    const int r = tid >> 3, c = tid & 7;
    const uint32_t so = r * 128 + ((c ^ (r & 7)) << 4);
    const __nv_bfloat16* wg0 = p.w + (size_t)r * (3 * DM) + hp * 64 + c * 8;
    const __nv_bfloat16* xg0 = p.x + (size_t)(2 * (gidx * 256 + r) + par) * DM + c * 8;
#pragma unroll
    for (int j = 0; j < 3; j++) cp_async16n(sb + OFF_1B + j * 4096 + so, wg0 + j * DM);
#pragma unroll
    for (int i = 0; i < 8; i++) cp_async16n(sb + i * 4096 + so, xg0 + (size_t)i * 64 * DM);
    asm volatile("cp.async.commit_group;\n" ::: "memory");
  }
  if (tid == 256) {
    prefetch_tmap(halo_cta ? &tmXh : &tmX);
#pragma unroll
    for (int i = 0; i < NS1B; i++) mbar_init(bars + 8 * (BAR_FULLB + i), 1);
#pragma unroll
    for (int i = 0; i < NS1A; i++) mbar_init(bars + 8 * (BAR_FULLA + i), 1);
    asm volatile("fence.mbarrier_init.release.cluster;\n" ::: "memory");
    if (!halo_cta && MODE != 2) {
      mbar_expect_tx(bars + 8 * (BAR_FULLB + 1), STG1B);
      tma_load_3d(sb + OFF_1B + 1 * STG1B, &tmW, bars + 8 * (BAR_FULLB + 1), hp * 64, 32, 0);
      mbar_expect_tx(bars + 8 * (BAR_FULLB + 2), STG1B);
      tma_load_3d(sb + OFF_1B + 2 * STG1B, &tmW, bars + 8 * (BAR_FULLB + 2), hp * 64, 64, 0);
    } else {
      prefetch_tmap(&tmWh);
    }
  } else if (tid == 288) {
#pragma unroll
    for (int i = 0; i < NS1A; i++) mbar_init(bars + 8 * (BAR_EMPTYA + i), 4);
#pragma unroll
    for (int i = 0; i < NS1B; i++) mbar_init(bars + 8 * (BAR_EMPTYB + i), 2);
    asm volatile("fence.mbarrier_init.release.cluster;\n" ::: "memory");
  } else if (tid == 320) {
#pragma unroll
    for (int i = 0; i < NS2; i++) {
      mbar_init(bars + 8 * (BAR_FULL2 + i), 1);
      mbar_init(bars + 8 * (BAR_EMPTY2 + i), 4);
    }
    mbar_init(bars + 8 * BAR_DEAD, 2);
    mbar_init(bars + 8 * (BAR_DEAD + 1), 2);
    mbar_init(bars + 8 * BAR_X, 2);
    mbar_init(bars + 8 * BAR_REL, 2);
    asm volatile("fence.mbarrier_init.release.cluster;\n" ::: "memory");
  } else if (tid == 352) {
    mbar_init(bars + 8 * BAR_T, 1);
    mbar_init(bars + 8 * BAR_UH, 3);
    mbar_init(bars + 8 * BAR_LFREE, 4);
    mbar_init(bars + 8 * BAR_LAND, 1);
    mbar_init(bars + 8 * BAR_U, 1);
    mbar_init(bars + 8 * BAR_Q, 1);
    mbar_init(bars + 8 * BAR_STG, 9);
    asm volatile("fence.mbarrier_init.release.cluster;\n" ::: "memory");
  }
  if (warp == 8) PROF2(23);
  cluster_sync_all();
  if (warp == 8) PROF2(24);

  if (warp >= 8) {
    const int hw = warp - 8;
    const int lr = lane & 7, lm = lane >> 3;
    auto g1_issue_a = [&](int j, int s) {
      const uint32_t fb = bars + 8 * (BAR_FULLA + s);
      mbar_expect_tx(fb, STG1A);
      tma_load_3d_mc(sb + s * STG1A + rank * 16384, &tmX, fb, j * 64, par, gidx * 256 + rank * 128);
    };
    auto g1_issue_b = [&](int kb, int s) {
      const uint32_t fb = bars + 8 * (BAR_FULLB + s);
      mbar_expect_tx(fb, STG1B);
      tma_load_3d(sb + OFF_1B + s * STG1B, &tmW, fb, hp * 64, kb * 32, 0);
    };
    asm volatile("setmaxnreg.dec.sync.aligned.u32 %0;\n" :: "n"(REG_HELP));

    if (halo_cta) {
      if (hw == 0) {
        int s = 0, ph = 1;
#pragma unroll 1
        for (int kb = 0; kb < 16; kb++) {
          mbar_wait(bars + 8 * (BAR_EMPTYB + s), ph);
          const uint32_t fb = bars + 8 * (BAR_FULLB + s), st = sb + s * STGH;
          if (elect_one()) {
            mbar_expect_tx(fb, STGH);
            tma_load_4d(st, &tmXh, fb, kb * 64, 248, 0, 0);
            tma_load_3d(st + 8192, &tmWh, fb, 0, kb * 64, 16 + blockIdx.x * 4);
            tma_load_3d(st + 8192 + 32768, &tmWh, fb, 0, kb * 64, 32 + blockIdx.x * 4);
          }
          if (++s == 3) { s = 0; ph ^= 1; }
        }
      }
      __syncwarp();
    } else if (hw == 0) {
      uint32_t epoch = 0;
      if (lane < (MODE == 2 ? NS2 : 2)) mbar_arrive_cluster_n(mapa(bars, rank) + 8 * (BAR_EMPTY2 + lane), 4);
      if (MODE != 2) {
      epoch = ld_relaxed(g_flag_o + 2 * cta) + 1;
      if (lane == 0) {
        mbar_expect_tx(bars + 8 * BAR_U, 32768);
        mbar_expect_tx(bars + 8 * BAR_LAND, 32768 + 64);
        mbar_expect_tx(bars + 8 * BAR_Q, 32768);
        mbar_expect_tx(bars + 8 * BAR_T, T_END);
      }
      {
        int sa = 1, pha = 1, sbb = 2, phb = 1;
#pragma unroll 1
        for (int kb = 2; kb < 32; kb++) {
          if (!(kb & 1)) {
            mbar_wait(bars + 8 * (BAR_EMPTYA + sa), pha);
            if (elect_one()) g1_issue_a(kb >> 1, sa);
            if (++sa == NS1A) { sa = 0; pha ^= 1; }
          }
          mbar_wait(bars + 8 * (BAR_EMPTYB + sbb), phb);
          if (kb > 2 && elect_one()) g1_issue_b(kb, sbb);
          __syncwarp();
          if (kb >= PF0 && kb < PF0 + 12)
            prefetch_l2((kb < PF0 + 8 ? p.q + (size_t)chb * 16384 + (kb - PF0) * 2048 : p.wo + (size_t)chb * 8192 + (kb - PF0 - 8) * 2048) + lane * 64);
          if (kb == 4) PROF2(27);
          if (kb == 1) PROF2(38);
          if (kb == 2) PROF2(39);
          if (++sbb == NS1B) { sbb = 0; phb ^= 1; }
        }
      }
      static_assert(32 % NS1B == 2 && (32 / NS1B) % 2 == 0 && OFF_Q == OFF_1B && 2 * STG1B == 6 * 4096, "slots / parity of these loads");
      const uint8_t* tab = reinterpret_cast<const uint8_t*>(g_tab);
      if (lane == 0) {
        prefetch_tmap(&tmWo);
        prefetch_tmap(&tmQ);
        bulk_load(sb + OFF_T + T_A1, tab + T_A1, T_END - T_A1, bars + 8 * BAR_T);
        mbar_wait(bars + 8 * (BAR_EMPTYB + 2), 1);
        tma_load_5d(sb + OFF_Q + 6 * 4096, &tmQ, bars + 8 * BAR_Q, (chb & ~1) * 8, rank * 32 + 24);
        tma_load_5d(sb + OFF_Q + 7 * 4096, &tmQ, bars + 8 * BAR_Q, (chb & ~1) * 8, rank * 32 + 28);
        if (gidx != 0) wait_flag(g_flag_h + (hp >> 2), epoch);
      }
      __syncwarp();
      {
        uint4 hk0 = make_uint4(0, 0, 0, 0), hk1 = hk0, hv0 = hk0, hv1 = hk0;
        if (gidx != 0) {
          const uint4* src = g_halo + cta * 128 + lane;
          hk0 = __ldcg(src); hk1 = __ldcg(src + 32); hv0 = __ldcg(src + 64); hv1 = __ldcg(src + 96);
        }
        if (lane == 0) {
          mbar_wait(bars + 8 * (BAR_EMPTYB + 3), 1);
          bulk_load(sb + OFF_T, tab, T_TW, bars + 8 * BAR_T);
        }
        __syncwarp();
        PROF2(18);
        sts128(sb + OFF_L0 + lane * 16, hk0.x, hk0.y, hk0.z, hk0.w);
        sts128(sb + OFF_L0 + 512 + lane * 16, hk1.x, hk1.y, hk1.z, hk1.w);
        stsm4(sb + OFF_L0 + 1024 + lr * 128 + ((lm ^ lr) << 4), hv0.x, hv0.y, hv0.z, hv0.w);
        stsm4(sb + OFF_L0 + 1024 + lr * 128 + (((4 + lm) ^ lr) << 4), hv1.x, hv1.y, hv1.z, hv1.w);
        __syncwarp();
        if (lane == 0) {
          mbar_arrive(bars + 8 * BAR_STG);
          mbar_wait(bars + 8 * (BAR_EMPTYB + 4), 1);
          bulk_load(sb + OFF_T + T_TW, tab + T_TW, T_A1 - T_TW, bars + 8 * BAR_T);
          if (MODE == 0) {
            mbar_expect_tx(bars + 8 * BAR_FULL2, STG2);
            mbar_expect_tx(bars + 8 * (BAR_FULL2 + 2), STG2);
            mbar_expect_tx(bars + 8 * (BAR_FULL2 + 3), STG2);
            tma_load_3d(sb + g2_b(0), &tmWo, bars + 8 * BAR_FULL2, 0, g2_k(hp, 0) * 64, cb2 * 2);
            tma_load_3d(sb + g2_b(1), &tmWo, bars + 8 * (BAR_FULL2 + 1), 0, g2_k(hp, 1) * 64, cb2 * 2);
          }
          mbar_wait(bars + 8 * BAR_EMPTYB, 0);
#pragma unroll 1
          for (int i = 0; i < 6; i++) tma_load_5d(sb + OFF_Q + i * 4096, &tmQ, bars + 8 * BAR_Q, (chb & ~1) * 8, rank * 32 + i * 4);
        }
        __syncwarp();
      }
      }
      if (MODE != 1) {
        auto korder = [&](int i) { return MODE == 2 ? i : g2_k(hp, i); };
        const __nv_bfloat16* osrc = g_o + (size_t)(rb2 >> 1) * 16 * 16384 + ((rb2 & 1) * 2 + rank) * 4096;
        const uint32_t* flag = g_flag_o + (rb2 >> 1) * 32 + korder(lane & 15) * 2 + (rb2 & 1);
        uint32_t ready = MODE == 0 ? 0u : ~0u, pv = 0;
        auto look = [&]() {
          ready |= __ballot_sync(0xffffffffu, pv == epoch);
          asm volatile("fence.acquire.gpu;\n" ::: "memory");
          fence_async_all();
        };
        const __nv_bfloat16* o23[2] = {osrc + korder(2) * 16384, osrc + korder(3) * 16384};
        if (MODE == 0) {
          asm volatile("" : "+l"(o23[0]), "+l"(o23[1]), "+l"(flag));
          mbar_wait_idle(bars + 8 * (BAR_EMPTY2 + 2), 0);
          mbar_wait(bars + 8 * (BAR_EMPTY2 + 3), 0);
          mbar_wait_idle(bars + 8 * BAR_REL, 0);
        }
#pragma unroll
        for (int i = MODE == 0 ? 2 : 0; i < 16; i++) {
          const int kb = korder(i), s = i % NS2, ph = (i / NS2) & 1;
          const uint32_t fb = bars + 8 * (BAR_FULL2 + s);
          if (!((ready >> i) & 1)) {
            int n = 0;
            do {
              ready |= __ballot_sync(0xffffffffu, ld_acquire(flag) == epoch);
            } while (!((ready >> i) & 1) && ++n < SPIN_LIMIT);
            fence_async_all();
          }
          if (i == 2) PROF(21);
          const bool pre = MODE == 0 && i < 4;
          if (!pre) mbar_wait(bars + 8 * (BAR_EMPTY2 + s), ph);
          if (elect_one()) {
            if (!pre) mbar_expect_tx(fb, STG2);
            asm volatile(
                "cp.async.bulk.shared::cluster.global.mbarrier::complete_tx::bytes.multicast::cluster [%0], [%1], %2, [%3], %4;\n"
                ::"r"(sb + g2_a(s, rb2 & 1) + rank * 8192), "l"(pre ? o23[i & 1] : osrc + kb * 16384), "r"(8192), "r"(fb), "h"((uint16_t)3) : "memory");
            if (!pre) tma_load_3d(sb + g2_b(s), &tmWo, fb, 0, kb * 64, cb2 * 2);
          }
          if (MODE == 0 && i == LA0) pv = ld_relaxed(flag);
          if (MODE == 0 && i == LA1) look();
          if (i == 3) PROF(37);

        }
      }
      __syncwarp();
    } else if (MODE != 2) {
      {
        const int g = lane >> 2, t = lane & 3;
        uint32_t w[2][4];
#pragma unroll
        for (int h = 0; h < 2; h++) {
          const uint2 x = __ldg(reinterpret_cast<const uint2*>(p.shift_k + ((chb & ~1) * 8 + h * 8 + g) * 4));
          w[h][0] = __byte_perm(x.x, x.x, 0x1010);
          w[h][1] = __byte_perm(x.x, x.x, 0x3232);
          w[h][2] = __byte_perm(x.y, x.y, 0x1010);
          w[h][3] = __byte_perm(x.y, x.y, 0x3232);
        }
        auto swz = [](int r) { return (((r & 29) | ((r ^ (r >> 2)) & 2)) << 5) | (r & 16); };
        const uint32_t kring = sb + OFF_H + (hw - 1) * 8192, vring = kring + 4096;
        const int s0 = rank * 32 + (hw - 1) * 11, s1 = hw == 3 ? rank * 32 + 32 : s0 + 11;
        const size_t goff = (size_t)(lane >> 1) * DM + (chb & ~1) * 8 + (lane & 1) * 8;
        const __nv_bfloat16* kg = p.k + goff;
        const __nv_bfloat16* vg = p.v + goff;
        const uint32_t d0 = swz(lane >> 1) ^ ((lane & 1) << 4), d1 = swz(16 + (lane >> 1)) ^ ((lane & 1) << 4);
        auto issue = [&](int st) {
          const uint32_t so = (st & 3) << 10;
          cp_async16(kring + so + d0, kg + (size_t)st * 32 * DM, 16);
          cp_async16(kring + so + d1, kg + (size_t)(st * 32 + 16) * DM, 16);
          cp_async16(vring + so + d0, vg + (size_t)st * 32 * DM, 16);
          cp_async16(vring + so + d1, vg + (size_t)(st * 32 + 16) * DM, 16);
        };
        const int xa = 8 * (lr >> 1) + 2 * lm + (lr & 1), xb = 8 * (lr >> 1) - 4 + 2 * (lm & 1) + (lr & 1);
        const uint32_t la = swz(xa), lb = swz(xb & 31);
        const int backb = xb < 0 ? 1 : 0;
        const uint32_t ud[2] = {mapa(sb + OFF_U + g * 4096 + t * 16, 0), mapa(sb + OFF_U + g * 4096 + t * 16, 1)};
        const uint32_t ub[2] = {mapa(bars + 8 * BAR_U, 0), mapa(bars + 8 * BAR_U, 1)};
        if (lane == 0) mbar_wait(bars + 8 * (BAR_FULLB + NS1B - 1), 0);
        __syncwarp();
        if (lane >= 24) cp_async16(kring + (((s0 - 1) & 3) << 10) + d1, s0 > 0 ? kg + (size_t)(s0 * 32 - 16) * DM : kg, s0 > 0 ? 16 : 0);
        issue(s0);
        asm volatile("cp.async.commit_group;\n" ::: "memory");
        issue(s0 + 1);
        asm volatile("cp.async.commit_group;\n" ::: "memory");
#pragma unroll 1
        for (int st = s0; st < s1; st++) {
          if (st + 2 < s1) issue(st + 2);
          if (hw == 1 && st - s0 < 8) prefetch_l2(p.ssm_k + (size_t)(chb * 8 + st - s0) * SEQ + lane * 64);
          if (hw == 2 && st == s0 + 4 && lane < 2) prefetch_l2(g_tab + (chb * 2 + lane) * 32);
          const uint32_t uo = (st ^ ((g ^ (st >> 2)) & 1)) * 64;
          asm volatile("cp.async.commit_group;\n" ::: "memory");
          asm volatile("cp.async.wait_group 2;\n" ::: "memory");
          __syncwarp();
#pragma unroll
          for (int h = 0; h < 2; h++) {
            uint32_t e[6], vv[4], e4[4];
            ldsm4t(e4, kring + ((st & 3) << 10) + (la ^ (h << 4)));
            ldsm2t(e[0], e[1], kring + (((st - backb) & 3) << 10) + (lb ^ (h << 4)));
            ldsm4t(vv, vring + ((st & 3) << 10) + (la ^ (h << 4)));
            e[2] = e4[0]; e[3] = e4[1]; e[4] = e4[2]; e[5] = e4[3];
            uint32_t o[5];
#pragma unroll
            for (int i = 0; i < 5; i++) o[i] = __byte_perm(e[i], e[i + 1], 0x5432);
#pragma unroll
            for (int i = 0; i < 4; i++) {
              uint32_t a = bmul2(o[i], w[h][3]);
              a = bfma2(e[i + 1], w[h][2], a);
              a = bfma2(o[i + 1], w[h][1], a);
              a = bfma2(e[i + 2], w[h][0], a);
              vv[i] = bmul2(a, vv[i]);
            }
            st_async128(ud[h] + uo, ub[h], vv[0], vv[1], vv[2], vv[3]);
          }
          __syncwarp();
        }
        PROF(16);
      }
      {
        const int rw = (lane >> 3) + (lane & 4), ck = lane & 3;
        const uint32_t so = rw * 64 + ck * 16, dof = rw * 128 + ((ck ^ rw) << 4);
        const uint8_t* hsrc = reinterpret_cast<const uint8_t*>(p.ssm_k + (size_t)chb * 8 * SEQ) + so;
        const float dv = lane < 8 ? __bfloat162float(p.ssm_D[chb * 8 + lane]) : 0.f;
        uint32_t x[32];
        auto load = [&](const uint8_t* src, int i) {
          asm volatile("ld.v4.u32 {%0,%1,%2,%3}, [%4];\n" : "=r"(x[4 * i]), "=r"(x[4 * i + 1]), "=r"(x[4 * i + 2]), "=r"(x[4 * i + 3])
                       : "l"(src + i * 512) : "memory");
        };
#pragma unroll
        for (int i = 0; i < 8; i++) load(hsrc + (hw - 1) * 4096, i);
        nb_sync(NB_HELP3, 96);
        mbar_wait(bars + 8 * BAR_U, 0);
        int eh = 0;
#pragma unroll 1
        for (int n = 2 * (hw - 1); n < 16; n += (n & 1) ? 5 : 1) {
          const int c = n >> 1;
          const uint8_t* nsrc = (n & 1) ? hsrc + (c < 5 ? c + 3 : c) * 4096
                                        : smem - OFF_L0 + OFF_U + c * 4096 + (so ^ (((c ^ (lane >> 2)) & 1) << 6));
          const uint32_t dst = sb + ((n & 1) ? OFF_U : OFF_H) + c * 4096 + dof;
          const float dc = __shfl_sync(0xffffffffu, dv, c);
          const float h0 = bf_lo(x[0]) + ((lane | (n & 1)) == 0 ? dc : 0.f), h1 = bf_hi(x[0]);
          x[0] = pack_bf16(h0, h1);
          uint32_t m[2] = {x[0], x[1]};
#pragma unroll
          for (int i = 2; i < 32; i++) asm("max.xorsign.abs.bf16x2 %0, %0, %1;\n" : "+r"(m[i & 1]) : "r"(x[i]));
          asm("max.xorsign.abs.bf16x2 %0, %0, %1;\n" : "+r"(m[0]) : "r"(m[1]));
          const uint32_t e = max(__reduce_max_sync(0xffffffffu, max((m[0] >> 7) & 255u, (m[0] >> 23) & 255u)), 5u);
          const uint32_t sc = (259u - e) * 0x00800080u;
#pragma unroll
          for (int i = 0; i < 8; i++) {
            uint32_t o[4];
#pragma unroll
            for (int j = 0; j < 4; j++) {
              const uint32_t v = bmul2(x[4 * i + j], sc);
              asm("cvt.rn.f16x2.f32 %0, %1, %2;\n" : "=r"(o[j]) : "f"(bf_hi(v)), "f"(i + j == 0 ? h0 * bf_hi(sc) : bf_lo(v)));
            }
            sts128((dst + (i & 3) * 1024) ^ ((i >> 2) << 6), o[0], o[1], o[2], o[3]);
            load(nsrc, i);
          }
          if (n & 1) {
            const int f = min(max((int)e + eh - 129, 0), 254);
            if (lane < 2)
              asm volatile("st.async.weak.shared::cluster.mbarrier::complete_tx::bytes.b32 [%0], %2, [%1];\n"
                           ::"r"(mapa(sb + OFF_SC + rank * 32 + c * 4, lane)), "r"(mapa(bars + 8 * BAR_LAND, lane)), "r"(f << 7) : "memory");
          }
          eh = e;
        }
        fence_async_smem();
        __syncwarp();
        if (lane == 0) mbar_arrive(bars + 8 * BAR_UH);
        PROF(32);
      }
      if (hw < 3) {
        const uint32_t rb = mapa(bars, lane & 1);
        const uint32_t epoch = ld_relaxed(g_flag_o + 2 * cta + hw - 1) + 1;
        const bool own = hw - 1 == (rb2 & 1);
        nb_sync(NB_OREADY + hw - 1, 160);
        if (lane == 0) {
          asm volatile("cp.async.bulk.global.shared::cta.bulk_group [%0], [%1], %2;\n" ::"l"(g_o + (size_t)cta * 16384 + (hw - 1) * 8192),
                       "r"(sb + OFF_OP + (hw - 1) * 16384), "r"(16384) : "memory");
          bulk_commit();
        }
        if (lane < 2) {
          mbar_arrive_cluster(rb + 8 * (BAR_EMPTY2 + 2));
          mbar_arrive_cluster(rb + 8 * (BAR_EMPTY2 + 3));
        }
        if (lane == 0) {
          bulk_wait0();
          if (own) mbar_expect_tx(bars + 8 * (BAR_FULL2 + 1), 16384);
          mbar_arrive_cluster(mapa(bars, own ? rank : rank ^ 1) + 8 * BAR_X);
          st_release(g_flag_o + 2 * cta + hw - 1, epoch);
          mbar_arrive(bars + 8 * BAR_REL);
        }
        __syncwarp();
        PROF(own ? 17 : 19);
      } else {
        if (MODE == 0) {
          mbar_wait_idle(bars + 8 * BAR_X, 0);
          if (elect_one())
            asm volatile("cp.async.bulk.shared::cluster.shared::cta.mbarrier::complete_tx::bytes [%0], [%1], %2, [%3];\n"
                         ::"r"(mapa(sb + g2_a(0, rb2 & 1), rank ^ 1)), "r"(sb + g2_a(1, rb2 & 1)), "r"(16384),
                         "r"(mapa(bars + 8 * BAR_FULL2, rank ^ 1)) : "memory");
        }
        if (MODE == 0) {
          mbar_wait_idle(bars + 8 * BAR_DEAD, 0);
          if (elect_one()) {
            tma_load_3d(sb + g2_b(2), &tmWo, bars + 8 * (BAR_FULL2 + 2), 0, g2_k(hp, 2) * 64, cb2 * 2);
            tma_load_3d(sb + g2_b(3), &tmWo, bars + 8 * (BAR_FULL2 + 3), 0, g2_k(hp, 3) * 64, cb2 * 2);
          }
        }
        __syncwarp();
      }
      {
        const int c8 = (4 * (lr >> 1) + 2 * (lm & 1) + (lr & 1)) & 7;
        const bool own = (lr >> 2) == rank;
        const uint32_t ya = sb + (own ? y_slot(c8 & 1, c8 >> 1) : OFF_LAND + c8 * 2048);
        const uint32_t yx = ((lm >> 1) ^ lr) << 4;
        const int row = (lane >> 4) * 8 + ((lane >> 3) & 1) * 16 + ((lane >> 2) & 1);
        uint2* og = reinterpret_cast<uint2*>(p.out + (size_t)(rank * 1024 + row) * (2 * DM) + (chb & ~1) * 8 + (lane & 3) * 4);
        const uint32_t qa = sb + OFF_Q + (lane >> 4) * 512 + (lane & 15) * 8;
        mbar_wait(bars + 8 * BAR_Q, 0);
        mbar_wait_idle(bars + 8 * BAR_LAND, 0);
        PROF(33);
        const uint32_t t0 = clock();
        const uint4 s4 = lds128(sb + OFF_SC + (lane & 3) * 16);
        const uint32_t sc[2] = {s4.x | (s4.y << 16), s4.z | (s4.w << 16)};
        auto fin = [&](uint32_t q2, uint32_t y2, uint32_t s2) {
          float lo, hi;
          asm("{\n.reg .b16 l, h;\nmov.b32 {l, h}, %2;\ncvt.f32.f16 %0, l;\ncvt.f32.f16 %1, h;\n}\n" : "=f"(lo), "=f"(hi) : "r"(y2));
          return bmul2(q2, bmul2(pack_bf16(lo, hi), s2));
        };
#pragma unroll 1
        for (int j = hw - 1; j < 16; j += 3) {
          uint32_t y[4][4];
          uint2 q[8];
          while ((uint32_t)clock() - t0 < j * PACE) __nanosleep(40);
          const uint32_t qj = qa + j * 2048;
#pragma unroll
          for (int i = 0; i < 4; i++) ldsm4t(y[i], ya + j * 128 + (yx ^ (i << 5)));
#pragma unroll
          for (int i = 0; i < 8; i++) q[i] = lds64(qj + (i >> 2) * 1024 + (i & 3) * 128);
#pragma unroll
          for (int i = 0; i < 8; i++) {
            og[(size_t)(j * 64 + (i >> 2) * 32 + (i & 3) * 2) * (2 * DM / 4)] =
                make_uint2(fin(q[i].x, y[i >> 1][2 * (i & 1)], sc[0]), fin(q[i].y, y[i >> 1][2 * (i & 1) + 1], sc[1]));
            if (i < 7) asm volatile("nanosleep.u32 %0;\n" ::"r"(FINE) : "memory");
          }
        }
      }
      PROF(22);
    }
    cluster_sync_all();
  } else {
    asm volatile("setmaxnreg.inc.sync.aligned.u32 %0;\n" :: "n"(REG_MATH));
    if (warp == 0) PROF2(26);
    const int wg = warp >> 2;
    const int wtid = tid & 127;
    const bool signaller = (wtid == 0) || (wtid == 32);
    const uint32_t rbars = mapa(bars, wtid >> 5 & 1);

    if (halo_cta) {
      const uint32_t epoch = ld_relaxed(g_flag_h + blockIdx.x) + 1;
      float acc0[64], acc1[64];
      int s = 0, ph = 0;
#pragma unroll 1
      for (int kb = 0; kb < 16; kb++) {
        mbar_wait(bars + 8 * (BAR_FULLB + s), ph);
        const uint32_t st = sb + s * STGH;
        const uint64_t da = mkdesc(st, 16, 1024, 1);
        const uint64_t db = mkdesc(st + 8192 + wg * 32768, 8192, 1024, 1);
        wg_fence();
#pragma unroll
        for (int kk = 0; kk < 4; kk++) {
          wgmma_n128(acc0, da + 2 * kk, db + 128 * kk, kb + kk);
          wgmma_n128(acc1, da + 2 * kk, db + 1024 + 128 * kk, kb + kk);
        }
        wg_commit();
        wg_wait<0>();
        if (wtid == 0) mbar_arrive(bars + 8 * (BAR_EMPTYB + s));
        if (++s == 3) { s = 0; ph ^= 1; }
      }
      fence_regs(acc0);
      fence_regs(acc1);
      if ((warp & 3) != 3) {
#pragma unroll
        for (int hh = 0; hh < 2; hh++) {
          uint4* dst = g_halo + ((hh * 4 + (warp & 3) + 1) * 16 + blockIdx.x * 4) * 128 + wg * 64 + lane;
#pragma unroll
          for (int j = 0; j < 4; j++) {
            const int o = 16 * j + 2 * hh;
            dst[(j >> 1) * 128 + (j & 1) * 32] =
                make_uint4(pack_bf16(acc0[o], acc0[o + 1]), pack_bf16(acc0[o + 4], acc0[o + 5]),
                           pack_bf16(acc0[o + 8], acc0[o + 9]), pack_bf16(acc0[o + 12], acc0[o + 13]));
            dst[(2 + (j >> 1)) * 128 + (j & 1) * 32] =
                make_uint4(pack_bf16(acc1[o], acc1[o + 1]), pack_bf16(acc1[o + 4], acc1[o + 5]),
                           pack_bf16(acc1[o + 8], acc1[o + 9]), pack_bf16(acc1[o + 12], acc1[o + 13]));
          }
        }
      }
      nb_sync(NB_G1DONE, 256);
      if (tid == 0) st_release(g_flag_h + blockIdx.x, epoch);
      PROF(36);
      cluster_sync_all();
      return;
    }

    float acc[64];
    auto g2_step = [&](int s, int kb) {
      const uint64_t da = mkdesc(sb + g2_a(s, rb2 & 1) + wg * 8192, 16, 1024, 1);
      const uint64_t db = mkdesc(sb + g2_b(s), 8192, 1024, 1);
      wg_fence();
      wgmma_n128(acc, da, db, kb);
      wgmma_n128(acc, da + 2, db + 128, 1);
      wgmma_n128(acc, da + 4, db + 256, 1);
      wgmma_n128(acc, da + 6, db + 384, 1);
      wg_commit();
    };

    if (MODE != 2) {
    uint32_t a1[2][4], tw[16], d1[32];
    const uint32_t tb = sb + OFF_T + wtid * 16;
    const uint64_t dx = mkdesc(sb + OFF_U + wg * 4096, OFF_H - OFF_U, 1024, 1);
    auto s1 = [&](int it) {
      hmma_n128t<0>(d1, a1[0], dx + it * 512);
      hmma_n128t<1>(d1, a1[1], dx + it * 512 + 128);
      wg_commit();
    };
    auto ldtw = [&](int i) {
      const uint4 v = lds128(tb + T_TW + i * 2048);
      tw[4 * i] = v.x; tw[4 * i + 1] = v.y; tw[4 * i + 2] = v.z; tw[4 * i + 3] = v.w;
    };
    {
      float acc0[96], acc1[96];
      int sa = 0, pha = 0, sbb = 0, phb = 0;
      asm volatile("cp.async.wait_group 0;\n" ::: "memory");
      fence_async_smem();
      nb_sync(NB_FIRST, 256);
      if (tid == 0) {
        mbar_arrive(bars + 8 * BAR_FULLA);
        mbar_arrive(bars + 8 * BAR_FULLB);
      }
      PROF(0 + wg);
#pragma unroll 1
      for (int kb = 0; kb < 30; kb++) {
        if (!(kb & 1)) mbar_wait(bars + 8 * (BAR_FULLA + sa), pha);
        mbar_wait(bars + 8 * (BAR_FULLB + sbb), phb);
        if (kb == 0) PROF2(0 + wg);
        if (kb == 4 && wg == 0) PROF2(28);
        if (kb == 8 && wg == 0) PROF2(29);
        if (kb == 16 && wg == 0) PROF2(30);
        const uint64_t da = mkdesc(sb + sa * STG1A + wg * 16384 + (kb & 1) * 64, 16, 1024, 1);
        const uint64_t db = mkdesc(sb + OFF_1B + sbb * STG1B, 4096, 1024, 1);
        wg_fence();
        wgmma_n192(acc0, da, db, kb);
        wgmma_n192(acc1, da + 512, db, kb);
        wgmma_n192(acc0, da + 2, db + 128, 1);
        wgmma_n192(acc1, da + 514, db + 128, 1);
        wg_commit();
        wg_wait<1>();
        if (kb > 0) {
          if (wtid == 64) mbar_arrive(bars + 8 * (BAR_EMPTYB + (sbb == 0 ? NS1B - 1 : sbb - 1)));
          if (!(kb & 1) && signaller) mbar_arrive_cluster(rbars + 8 * (BAR_EMPTYA + (sa == 0 ? NS1A - 1 : sa - 1)));
        }
        if (++sbb == NS1B) { sbb = 0; phb ^= 1; }
        if ((kb & 1) && ++sa == NS1A) { sa = 0; pha ^= 1; }
      }
      const int blk0 = wg * 8 + (warp & 3);
      const int lr = lane & 7, lm = lane >> 3;
      const bool le0 = 2 * (lane & 3) <= (lane >> 2), le1 = 2 * (lane & 3) + 1 <= (lane >> 2);
      const uint32_t maskLE = (le0 ? 0x0000FFFFu : 0u) | (le1 ? 0xFFFF0000u : 0u);
      uint32_t k0[2][2][4], k1[2][2][4], qa[2][2][8];
      float l[2][2][4];
      {
        static_assert(15 % NS1A == 0 && 30 % NS1B == 0, "slots of the last k blocks");
        mbar_wait(bars + 8 * BAR_FULLA, 1);
        mbar_wait(bars + 8 * BAR_FULLB, 0);
        mbar_wait(bars + 8 * (BAR_FULLB + 1), 0);
        mbar_wait(bars + 8 * (BAR_EMPTYB + 2), 1);
        const uint64_t da = mkdesc(sb + wg * 16384, 16, 1024, 1);
        const uint64_t db = mkdesc(sb + OFF_1B, 4096, 1024, 1);
        wg_fence();
#pragma unroll
        for (int i = 0; i < 4; i++) wgmma_n192(acc0, da + 2 * i, db + (i >> 1) * (STG1B >> 4) + (i & 1) * 128, 1);
        wg_commit();
        wg_wait<1>();
        if (wtid == 64) mbar_arrive(bars + 8 * (BAR_EMPTYB + NS1B - 1));
#pragma unroll
        for (int i = 0; i < 2; i++) wgmma_n192(acc1, da + 512 + 2 * i, db + (i >> 1) * (STG1B >> 4) + (i & 1) * 128, 1);
        wg_commit();
        wg_wait<1>();
        fence_regs(acc0);
        attn_stage(sb, blk0, lane, acc0, k1[0]);
#pragma unroll
        for (int i = 2; i < 4; i++) wgmma_n192(acc1, da + 512 + 2 * i, db + (i >> 1) * (STG1B >> 4) + (i & 1) * 128, 1);
        wg_commit();
        attn_pack(acc0, qa[0], k0[0]);
        wg_wait<0>();
        fence_regs(acc1);
      }
      if (wtid == 64) mbar_arrive(bars + 8 * BAR_EMPTYB);
      PROF(2 + wg);
      attn_stage(sb, blk0 + 4, lane, acc1, k1[1]);
      __syncwarp();
      if (lane == 0) mbar_arrive(bars + 8 * BAR_STG);
      mbar_wait(bars + 8 * BAR_U, 0);
      attn_pack(acc1, qa[1], k0[1]);
      attn_own(k0[0], k1[0], le0, le1, qa[0], l[0]);
      attn_own(k0[1], k1[1], le0, le1, qa[1], l[1]);
      static_assert(OFF_L0 + 2048 == OFF_VP, "halo V rows");
      const uint32_t vl0 = sb + OFF_VP - 1024 + blk0 * 2048 + (lm >> 1) * 1024 + lr * 128 + (((lm & 1) ^ lr) << 4);
      const uint32_t vl[4] = {vl0, vl0 ^ 64, vl0 ^ 32, vl0 ^ 96};
      const uint32_t obase = sb + OFF_OP + (blk0 * 16 + lr) * 128 + ((lm ^ lr) << 4);
      mbar_wait(bars + 8 * BAR_STG, 0);
      {
        uint32_t km[4][4], va[8][4], vb[8][4], pp[8];
        float x[8][2];
#pragma unroll
        for (int n = 0; n < 4; n++) {
          const int blk = blk0 + 4 * (n >> 1);
          to_arr(km[n], lds128(sb + (blk == 0 ? OFF_L0 : OFF_OP + blk * 2048) + (n & 1) * 512 + lane * 16));
        }
#pragma unroll
        for (int n = 0; n < 8; n++) {
          const uint32_t o = ((n >> 1) & 1) * 8192 + (n >> 2) * 1024;
          ldsm4t(va[n], vl[n & 1] + o);
          ldsm4t(vb[n], vl[2 + (n & 1)] + o);
        }
        const bool first = blk0 == 0 && gidx == 0;
#pragma unroll
        for (int n = 0; n < 4; n++) {
          const uint32_t(&q)[8] = qa[n >> 1][n & 1];
          float sm[4];
          mma16816_z(sm, q[0], q[1], q[2], q[3], km[n][0], km[n][1]);
          mma16816(sm, q[4], q[5], q[6], q[7], km[n][2], km[n][3]);
          if (n < 2 && first) sm[0] = sm[1] = -1e9f / 0.17677669529663687f;
          x[n][0] = le0 ? l[n >> 1][n & 1][0] : sm[0];
          x[n][1] = le1 ? l[n >> 1][n & 1][1] : sm[1];
          x[4 + n][0] = l[n >> 1][n & 1][2];
          x[4 + n][1] = l[n >> 1][n & 1][3];
        }
        quad_softmax<8>(x, pp);
#pragma unroll
        for (int n = 7; n >= 0; n--)
          attn_pv((obase ^ ((n & 1) << 6)) + ((n >> 1) & 1) * 8192 + (n >> 2) * 1024, va[n], vb[n], pp[n], maskLE);
      }
      fence_async_smem();
      nb_arrive(NB_OREADY + wg, 160);
    }

    {
      const int w = warp & 3;
      uint32_t a4[8][4];
      uint32_t d4[16];
      PROF(34 + wg);
      const uint64_t dz = mkdesc(sb + OFF_U + wg * 4096, 1024, 128, 0);
      const uint64_t db2 = mkdesc(sb + OFF_T + T_B2, 128, 256, 0);
      mbar_wait(bars + 8 * BAR_T, 0);
      mbar_wait(bars + 8 * BAR_UH, 0);
      to_arr(a1[0], lds128(tb + T_A1));
      to_arr(a1[1], lds128(tb + T_A1 + 2048));
      wg_fence();
      s1(0);
      ldtw(0);
      ldtw(1);
      const uint32_t za = sb + (w < 2 ? OFF_U : OFF_H) + wg * 4096 + (w & 1) * 8192 + lane * 16;
      const uint32_t yl = (wtid ^ (4 * rank + wg)) * 16;
      const uint32_t yown = mapa(sb, rank) + yl, yrem = mapa(sb + OFF_LAND + wg * 2048, rank ^ 1) + yl;
      const uint32_t yb[2] = {mapa(bars + 8 * BAR_LAND, 0), mapa(bars + 8 * BAR_LAND, 1)};
      wg_wait<0>();
      fence_regs(d1);
      auto s4 = [&]() {
        wg_fence();
#pragma unroll
        for (int ks = 0; ks < 8; ks++) {
          const uint64_t d = dz + (ks & 1) * 128 + ((ks >> 1) & 1) * 512 + (ks >> 2) * ((OFF_H - OFF_U) >> 4);
          if (ks == 0) hmma_n64t<0>(d4, a4[ks], d);
          else hmma_n64t<1>(d4, a4[ks], d);
        }
        wg_commit();
      };
      auto e4 = [&](int pr) {
        fence_regs(d4);
        mbar_wait(bars + 8 * (pr == 0 ? BAR_LFREE : BAR_DEAD + 1), 0);
#pragma unroll
        for (int u = 0; u < 2; u++) {
          const int it = 2 * pr + u;
          const uint32_t o = (yown + y_slot(wg, it)) ^ (pr << 5), m = (yrem + it * 4096) ^ (pr << 5);
          st_async128(rank ? m : o, yb[0], d4[8 * u], d4[8 * u + 1], d4[8 * u + 2], d4[8 * u + 3]);
          st_async128(rank ? o : m, yb[1], d4[8 * u + 4], d4[8 * u + 5], d4[8 * u + 6], d4[8 * u + 7]);
        }
      };
      uint32_t a2[2][2][2][4], a3[2][2][4], d2[2][2][8], d3[2][8];
      auto s2a = [&]() {
        wg_fence();
#pragma unroll
        for (int c = 0; c < 4; c++) hmma_n32<0, 0>(d2[c & 1][c >> 1], a2[0][c & 1][c >> 1], db2 + (c >> 1) * 128);
      };
      auto s2b = [&]() {
        wg_fence();
#pragma unroll
        for (int c = 0; c < 4; c++) {
          hmma_n32<1, 0>(d2[c & 1][c >> 1], a2[1][c & 1][c >> 1], db2 + (c >> 1) * 128 + 64);
          if (c & 1) wg_commit();
        }
      };
      fft_e1<0>(d1, tw, a2[0]);
      s2a();
      fft_e1<1>(d1, tw, a2[1]);
      s2b();
      s1(1);
      ldtw(2);
      ldtw(3);
#pragma unroll
      for (int i = 0; i < 8; i++) to_arr(a4[i], lds128(tb + T_A4 + i * 2048));
#pragma unroll
      for (int it = 0; it < 4; it++) {
        if (it == 2) wg_wait<3>(); else if (it == 3) wg_wait<1>(); else wg_wait<2>();
        fence_regs(d2[0][0]);
        fence_regs(d2[1][0]);
        fft_e2<0, 0>(d2[0][0], d2[1][0], a3[0]);
        fft_e2<0, 1>(d2[0][0], d2[1][0], a3[1]);
        if (it == 2) wg_wait<2>(); else if (it == 3) wg_wait<0>(); else wg_wait<1>();
        fence_regs(d2[0][1]);
        fence_regs(d2[1][1]);
        fft_e2<1, 0>(d2[0][1], d2[1][1], a3[0]);
        fft_e2<1, 1>(d2[0][1], d2[1][1], a3[1]);
        wg_fence();
        hmma_n32<0, 0>(d3[0], a3[0][0], db2);
        hmma_n32<0, 0>(d3[1], a3[0][1], db2);
        hmma_n32<1, 0>(d3[0], a3[1][0], db2 + 64);
        hmma_n32<1, 0>(d3[1], a3[1][1], db2 + 64);
        wg_commit();
        if (it < 3) {
          wg_wait<1>();
          if (it == 2) {
            if (wtid == 64) mbar_arrive(bars + 8 * BAR_DEAD);
            e4(0);
          }
          fence_regs(d1);
          fft_e1<0>(d1, tw, a2[0]);
        }
        wg_wait<0>();
        if (it == 3 && wtid == 64) mbar_arrive(bars + 8 * (BAR_DEAD + 1));
        fence_regs(d3[0]);
        fence_regs(d3[1]);
        if (it < 3) s2a();
        fft_e3(d3, tw, za + (it & 1) * 512);
        if (it < 3) {
          fft_e1<1>(d1, tw, a2[1]);
          s2b();
        }
        if (it & 1) {
          fence_async_smem();
          nb_sync(NB_WG + wg, 128);
          if (it == 1 && signaller) mbar_arrive_cluster(rbars + 8 * BAR_LFREE);
          s4();
        }
        if (it < 2) s1(it + 2);
        if (w == 0) PROF3(40 + 4 * wg + it);
      }
      if (PEEL && MODE == 0) {
        mbar_wait(bars + 8 * BAR_FULL2, 0);
        g2_step(0, 0);
        wg_wait<1>();
      } else {
        wg_wait<0>();
      }
      if (signaller) mbar_arrive_cluster(rbars + 8 * (BAR_EMPTY2 + 4));
      e4(1);
      if (PEEL && MODE == 0) {
        wg_wait<0>();
        if (signaller) mbar_arrive_cluster(rbars + 8 * BAR_EMPTY2);
      }
      PROF(6 + wg);
    }
    }

    if (MODE != 1) {
      int s = PEEL && MODE == 0, ph = 0;
#pragma unroll 1
      for (int kb = s; kb < STAG; kb++) {
        mbar_wait(bars + 8 * (BAR_FULL2 + s), ph);
        if (kb == 1) PROF(8 + wg);
        if (warp == 4) PROF2(40 + kb);
        g2_step(s, kb);
        wg_wait<0>();
        if (kb < 16 - NS2 && signaller) mbar_arrive_cluster(rbars + 8 * (BAR_EMPTY2 + s));
        if (++s == NS2) { s = 0; ph ^= 1; }
      }
      if (STAG < 16) {
        if (wg == LAST) nb_sync(NB_LEAD, 256);
#pragma unroll
        for (int kb = STAG; kb < 16; kb++) {
          mbar_wait(bars + 8 * (BAR_FULL2 + kb % NS2), (kb / NS2) & 1);
          g2_step(kb % NS2, 1);
        }
        if (wg != LAST) nb_arrive(NB_LEAD, 256);
      }
      wg_wait<0>();
      fence_regs(acc);
      PROF(10 + wg);
      const int lr = lane & 7, lm = lane >> 3;
      const uint32_t wbase = sb + warp * 2048;
      const uint32_t base = wbase + (lr + 8 * (lm & 1)) * 128;
#pragma unroll
      for (int j = 0; j < 16; j += 2) {
        const uint32_t a = base + (j >> 3) * 16384 + ((((j & 7) + (lm >> 1)) ^ lr) << 4);
        stsm4(a, pack_bf16(acc[4 * j], acc[4 * j + 1]), pack_bf16(acc[4 * j + 2], acc[4 * j + 3]),
              pack_bf16(acc[4 * j + 4], acc[4 * j + 5]), pack_bf16(acc[4 * j + 6], acc[4 * j + 7]));
      }
      __syncwarp();
      {
        const int rr = lane >> 4, ck = lane & 7, hf = (lane >> 3) & 1;
        uint4* og = reinterpret_cast<uint4*>(p.out + (size_t)(2 * ((rb2 & 7) * 128 + warp * 16 + rr) + (rb2 >> 3)) * (2 * DM) + DM + cb2 * 128 + hf * 64 + ck * 8);
        uint4 v[8];
#pragma unroll
        for (int i = 0; i < 8; i++) v[i] = lds128(wbase + hf * 16384 + (2 * i + rr) * 128 + ((ck ^ ((2 * i + rr) & 7)) << 4));
#pragma unroll
        for (int i = 0; i < 8; i++) og[(size_t)i * 4 * (2 * DM / 8)] = v[i];
      }
      PROF(12 + wg);
    }
    cluster_sync_all();
  }
}

typedef CUresult (*EncodeFn)(CUtensorMap*, CUtensorMapDataType, cuuint32_t, void*, const cuuint64_t*, const cuuint64_t*,
                             const cuuint32_t*, const cuuint32_t*, CUtensorMapInterleave, CUtensorMapSwizzle,
                             CUtensorMapL2promotion, CUtensorMapFloatOOBfill);

void make_map(EncodeFn enc, CUtensorMap* tm, const void* base, int rank, const cuuint64_t* dims, const cuuint64_t* strides,
              const cuuint32_t* box, CUtensorMapSwizzle swz) {
  cuuint32_t es[5] = {1, 1, 1, 1, 1};
  enc(tm, CU_TENSOR_MAP_DATA_TYPE_BFLOAT16, rank, const_cast<void*>(base), dims, strides, box, es,
      CU_TENSOR_MAP_INTERLEAVE_NONE, swz, CU_TENSOR_MAP_L2_PROMOTION_L2_256B, CU_TENSOR_MAP_FLOAT_OOB_FILL_NONE);
}

}

extern "C" void kernel_launch(void* const* d_in, const int* in_sizes, int n_in, void* d_out, int out_size) {
  static EncodeFn enc = nullptr;
  static bool coresident = true;
  if (!enc) {
    void* fn = nullptr;
    cudaDriverEntryPointQueryResult qr;
    cudaGetDriverEntryPoint("cuTensorMapEncodeTiled", &fn, cudaEnableDefault, &qr);
    enc = (EncodeFn)fn;
    cudaFuncSetAttribute(fused_kernel<0>, cudaFuncAttributeMaxDynamicSharedMemorySize, SMEM_BYTES);
    cudaFuncSetAttribute(fused_kernel<1>, cudaFuncAttributeMaxDynamicSharedMemorySize, SMEM_BYTES);
    cudaFuncSetAttribute(fused_kernel<2>, cudaFuncAttributeMaxDynamicSharedMemorySize, SMEM_BYTES);
    cudaLaunchConfig_t cfg = {};
    cfg.gridDim = dim3(NCTA);
    cfg.blockDim = dim3(NTHREADS);
    cfg.dynamicSmemBytes = SMEM_BYTES;
    cudaLaunchAttribute at;
    at.id = cudaLaunchAttributeClusterDimension;
    at.val.clusterDim.x = 2;
    at.val.clusterDim.y = 1;
    at.val.clusterDim.z = 1;
    cfg.attrs = &at;
    cfg.numAttrs = 1;
    int nclusters = 0;
    if (cudaOccupancyMaxActiveClusters(&nclusters, fused_kernel<0>, &cfg) == cudaSuccess) coresident = nclusters >= NCTA / 2;
    (void)cudaGetLastError();
  }
  CUtensorMap tmX, tmW, tmWo, tmQ, tmXh, tmWh;
  {
    cuuint64_t dims[3] = {1024, 2, 1024};
    cuuint64_t str[2] = {2048, 4096};
    cuuint32_t box[3] = {64, 1, 128};
    make_map(enc, &tmX, d_in[6], 3, dims, str, box, CU_TENSOR_MAP_SWIZZLE_128B);
  }
  {
    cuuint64_t dims[3] = {1024, 1024, 3};
    cuuint64_t str[2] = {6144, 2048};
    cuuint32_t box[3] = {64, 32, 3};
    make_map(enc, &tmW, d_in[7], 3, dims, str, box, CU_TENSOR_MAP_SWIZZLE_128B);
  }
  {
    cuuint64_t dims[3] = {64, 1024, 16};
    cuuint64_t str[2] = {2048, 128};
    cuuint32_t box[3] = {64, 64, 2};
    make_map(enc, &tmWo, d_in[8], 3, dims, str, box, CU_TENSOR_MAP_SWIZZLE_128B);
  }
  {
    cuuint64_t dims[5] = {1024, 2, 2, 8, 64};
    cuuint64_t str[4] = {2048, 16 * 2048, 2 * 2048, 32 * 2048};
    cuuint32_t box[5] = {16, 2, 2, 8, 4};
    make_map(enc, &tmQ, d_in[0], 5, dims, str, box, CU_TENSOR_MAP_SWIZZLE_NONE);
  }
  {
    cuuint64_t dims[4] = {1024, 256, 2, 4};
    cuuint64_t str[3] = {4096, 2048, 256 * 4096};
    cuuint32_t box[4] = {64, 8, 2, 4};
    make_map(enc, &tmXh, d_in[6], 4, dims, str, box, CU_TENSOR_MAP_SWIZZLE_128B);
  }
  {
    cuuint64_t dims[3] = {64, 1024, 48};
    cuuint64_t str[2] = {6144, 128};
    cuuint32_t box[3] = {64, 64, 4};
    make_map(enc, &tmWh, d_in[7], 3, dims, str, box, CU_TENSOR_MAP_SWIZZLE_128B);
  }
  Params p;
  p.q = (const __nv_bfloat16*)d_in[0];
  p.k = (const __nv_bfloat16*)d_in[1];
  p.v = (const __nv_bfloat16*)d_in[2];
  p.shift_k = (const __nv_bfloat16*)d_in[3];
  p.ssm_k = (const __nv_bfloat16*)d_in[4];
  p.ssm_D = (const __nv_bfloat16*)d_in[5];
  p.x = (const __nv_bfloat16*)d_in[6];
  p.w = (const __nv_bfloat16*)d_in[7];
  p.wo = (const __nv_bfloat16*)d_in[8];
  p.out = (__nv_bfloat16*)d_out;
  if (coresident) {
    fused_kernel<0><<<NCTA, NTHREADS, SMEM_BYTES>>>(p, tmX, tmW, tmWo, tmQ, tmXh, tmWh);
  } else {
    fused_kernel<0><<<4, NTHREADS, SMEM_BYTES>>>(p, tmX, tmW, tmWo, tmQ, tmXh, tmWh);
    fused_kernel<1><<<NCTA, NTHREADS, SMEM_BYTES>>>(p, tmX, tmW, tmWo, tmQ, tmXh, tmWh);
    fused_kernel<2><<<NCTA, NTHREADS, SMEM_BYTES>>>(p, tmX, tmW, tmWo, tmQ, tmXh, tmWh);
  }
}
```

```cpp
#include <cuda_runtime.h>
#include <cuda.h>
#include <cuda_bf16.h>
#include <stdint.h>

namespace {

constexpr int SEQ = 2048;
constexpr int DM = 1024;
constexpr int NCTA = 132;
constexpr int NTHREADS = 384;

constexpr int STG1A = 32768;
constexpr int NS1A = 3;
constexpr int STG1B = 12288;
constexpr int NS1B = 5;
constexpr int OFF_1B = NS1A * STG1A;
constexpr int STG2 = 32768;
constexpr int NS2 = 5;
constexpr int STGH = 73728;
constexpr int OFF_VP = 0;
constexpr int OFF_KH = 1 * STG2;
constexpr int OFF_OP = 2 * STG2;
constexpr int OFF_Q = 3 * STG2;
constexpr int T_A4 = 0, T_TW = 16384, T_B2 = 24576, T_A1 = 28672, T_END = 32768;
constexpr int OFF_U = 163840;
constexpr int OFF_H = OFF_U + 32768;
constexpr int OFF_T = OFF_U - T_END;
constexpr int OFF_LAND = 4 * STG2;
constexpr int OFF_BAR = OFF_H + 32768;
constexpr int OFF_SC = OFF_BAR + 512;
constexpr int OFF_L0 = -2048;
constexpr int SMEM_BYTES = 2048 + OFF_BAR + 1024;
static_assert(OFF_T + T_A1 == OFF_1B + NS1B * STG1B && OFF_T + T_TW == OFF_1B + 4 * STG1B && OFF_LAND == OFF_T + T_A4, "layout");
static_assert(3 * STGH <= OFF_BAR && SMEM_BYTES <= 232448, "smem");

constexpr int BAR_FULLA = 0;
constexpr int BAR_EMPTYA = 3;
constexpr int BAR_FULLB = 6;
constexpr int BAR_EMPTYB = 11;
constexpr int BAR_FULL2 = 16;
constexpr int BAR_EMPTY2 = 21;
constexpr int BAR_T = 26;
constexpr int BAR_UH = 27;
constexpr int BAR_LFREE = 28;
constexpr int BAR_LAND = 29;
constexpr int BAR_U = 30;
constexpr int BAR_Q = 31;
constexpr int BAR_STG = 32;
constexpr int BAR_DEAD = 33;
constexpr int BAR_X = 35;
constexpr int BAR_REL = 36;

constexpr int NB_G1DONE = 1;
constexpr int NB_OREADY = 2;
constexpr int NB_WG = 4;
constexpr int NB_HELP3 = 6;
constexpr int NB_FIRST = 7;
constexpr int NB_LEAD = 8;

#define PACE 390u
#define PF0 20
#define PEEL 1
#define IDLEW 1
#define LA0 3
#define LA1 4
#define STAG 12
#define LAST 0
#define FINE 40
#define F4 1
#define S1FIRST 0
#define REG_MATH 224
#define REG_HELP 56
constexpr int SPIN_LIMIT = 1 << 20;

__device__ __align__(1024) __nv_bfloat16 g_o[SEQ * DM];
__device__ __align__(128) uint32_t g_flag_o[256];
__device__ uint32_t g_flag_h[4];
__device__ uint4 g_halo[128 * 128];
__device__ __align__(128) const uint32_t g_tab[T_END / 4] = {
0x3c003c00,0x3bf13bff,0,0xafd6a648,0x3c003c00,0x3b993bce,0,0xb505b303,0x3c003c00,0x3af63b50,0,0xb7e3b67c,
0x3c003c00,0x3a0f3a8a,0,0xb93ab89b,0x3bc33bfe,0x3b773bfa,0xb3c6aa48,0xb5c2acb5,0x3a6d3b3b,0x389b3a4f,0xb8c4b6d7,0xba8ab8ec,
0x381d395f,0x26483505,0xbaddb9ed,0xbbffbb99,0x30b23564,0xb848b444,0xbbeabb88,0xbac2bbb6,0x3b0e3bf6,0x3a8a3bf1,0xb78bae46,0xb89bafd6,
0x34a53913,0xa6483732,0xbba8ba2f,0xbbffbb25,0xb78bae46,0xbac2b7e3,0xbb0ebbf6,0xb848baf6,0xbba8ba2f,0xbb50bbfa,0xb4a5b913,0x367cacb5,
0x39ed3bea,0x393a3be2,0xb95fb0b2,0xba0fb179,0xb56433c6,0xb8ec2648,0xbb88bbc3,0xba4fbbff,0xbbfeba6d,0xbb25bbce,0xaa48b8c4,0x3732b303,
0xb6d7badd,0x3444b67c,0x3b3b381d,0x3bb63b50,0x38723bd9,0x37323bce,0xbaa7b23e,0xbb25b303,0xbaa7b23e,0xbbb6b67c,0xb872bbd9,0xb444bb50,
0xb872bbd9,0xacb5ba8a,0x3aa7323e,0x3bfa389b,0x3aa7323e,0x3bf139cb,0x38723bd9,0xafd63984,0x35643bc3,0x33033bb6,0xbb88b3c6,0xbbceb444,
0xbbfeb8c4,0xbb77ba0f,0x2a48ba6d,0x35c2b93a,0x36d7b81d,0x3a8aafd6,0x3b3b3add,0x389b3bf1,0x395f3bea,0x26483b25,0xb9ed30b2,0xbbffb732,
0x2e463ba8,0xa6483b99,0xbbf6b4a5,0xbbffb505,0xba2fbb0e,0xb848bbb6,0x3913b78b,0x3ac2b444,0x3bf634a5,0x3b50393a,0x2e463ba8,0xb67c3a0f,
0xb913378b,0xbbe2afd6,0xba2fbb0e,0xb179bbf1,0xb0b23b88,0xb4443b77,0xbbeab564,0xbbb6b5c2,0xb3c6bbfe,0x2cb5bbe2,0x3bc3aa48,0x3bfa3179,
0x38c43b3b,0x2fd63bff,0xba6d36d7,0xbbf12648,0xbaddb95f,0xb505bbce,0x381db9ed,0x3b99b303,0xb61f3b64,0xb7e33b50,0xbb64b61f,0xbaf6b67c,
0x361fbb64,0x393aba8a,0x3b64361f,0x3a0f389b,0xb61f3b64,0xba4f3984,0xbb64b61f,0xb8ecb9cb,0x361fbb64,0x3b25b848,0x3b64361f,0x37323ac2,
0xb8c43b3b,0xb9843b25,0xba6db6d7,0xb9cbb732,0x3addb95f,0x3bceb7e3,0x381d39ed,0x33033af6,0xbbea3564,0xbb77acb5,0xb0b2bb88,0x35c2bbfa,
0x3bc32a48,0x389b38ec,0xb3c63bfe,0xba8a3a4f,0xba2f3b0e,0xbac23af6,0xb913b78b,0xb848b7e3,0x3bf6b4a5,0x3b50acb5,0xae463ba8,0xb67c3bfa,
0xb913b78b,0xb179ba4f,0x3a2fbb0e,0x3be2b8ec,0xae463ba8,0xb9cb3b99,0xbbf634a5,0xb984b505,0xbb3b3add,0xbb993ac2,0xb6d7b81d,0xb505b848,
0x39ed30b2,0x37e335c2,0xb95f3bea,0xbaf63b77,0x3564bbc3,0x3a0fbbe2,0x3b88b3c6,0x393a3179,0xbbfe38c4,0xba4f2648,0xaa48ba6d,0x38ecbbff,
0xbbd93aa7,0xbbfa3a8a,0xb23eb872,0xacb5b89b,0x323e3872,0xafd639cb,0xbbd93aa7,0xbbf13984,0x3bd9baa7,0x3b99b848,0x323e3872,0xb5053ac2,
0xb23eb872,0x37e3bb77,0x3bd9baa7,0x3af6b5c2,0xbbfe3a6d,0xbbe23a4f,0x2a48b8c4,0x3179b8ec,0xb6d73add,0xb9843b99,0xbb3b381d,0xb9cb3505,
0x395fb0b2,0x33033444,0xb9ed3bea,0xbbce3bb6,0x3b88bbc3,0x3b77b93a,0x356433c6,0xb5c23a0f,0xbba83a2f,0xbb503a0f,0x34a5b913,0x367cb93a,
0xbb0e3bf6,0xbbe23bf1,0xb78b2e46,0xb179afd6,0xb4a53913,0xb9cb3b25,0xbba83a2f,0xb9843732,0x378bae46,0xb30337e3,0xbb0e3bf6,0xbbce3af6,
0xbadd39ed,0xba4f39cb,0x381db95f,0x38ecb984,0xbbea3b88,0xbb253ac2,0x30b2b564,0x3732b848,0xbbc33bfe,0xbbb63b77,0xb3c62a48,0x3444b5c2,
0xba6d3b3b,0xbbfa3be2,0xb8c436d7,0x2cb5b179,0xb9a839a8,0xb8ec3984,0x39a8b9a8,0x3a4fb9cb,0xb9a839a8,0xb7323848,0x39a8b9a8,0x3b25bac2,
0xb9a839a8,0xb44435c2,0x39a8b9a8,0x3bb6bb77,0xb9a839a8,0xacb53179,0x39a8b9a8,0x3bfabbe2,0xb81d395f,0xb67c393a,0x3addb9ed,0x3b50ba0f,
0xb0b23564,0x31792fd6,0x3beabb88,0x3be2bbf1,0x33c6aa48,0x3984b732,0x3bc3bbfe,0x39cbbb25,0x38c4b6d7,0x3bcebaf6,0x3a6dbb3b,0x3303b7e3,
0xb4a53913,0xb17938ec,0x3ba8ba2f,0x3be2ba4f,0x378bae46,0x39cbb505,0x3b0ebbf6,0x3984bb99,0x3ba8ba2f,0x3bcebbb6,0x34a5b913,0xb303b444,
0x3b0ebbf6,0x35c2ba0f,0xb78b2e46,0xbb77393a,0xaa4838c4,0x2cb5389b,0x3bfeba6d,0x3bfaba8a,0x3b3bb81d,0x3bf1b984,0x36d7badd,0x2fd6b9cb,
0x39edbbea,0x3505bac2,0xb95f30b2,0xbb993848,0xb564b3c6,0xbaf635c2,0xbb883bc3,0xb7e33b77,0x323e3872,0x35053848,0x3bd9baa7,0x3b99bac2,
0x3bd9baa7,0x3af6bb77,0xb23eb872,0xb7e3b5c2,0xb23eb872,0xb93ab179,0xbbd93aa7,0xba0f3be2,0xbbd93aa7,0xb8ec3bff,0x323e3872,0x3a4fa648,
0x36d7381d,0x384837e3,0x3b3bbadd,0x3ac2baf6,0x395fbbea,0x367cbbfa,0xb9edb0b2,0xbb502cb5,0xbb8833c6,0xbbe238ec,0xb5643bc3,0x31793a4f,
0x2a483a6d,0x39843505,0x3bfeb8c4,0x39cbbb99,0x3913378b,0x39cb3732,0x3a2fbb0e,0x3984bb25,0x2e46bba8,0xb303baf6,0xbbf634a5,0xbbce37e3,
0xba2f3b0e,0xb5c23bfa,0x3913378b,0x3b772cb5,0x3bf6b4a5,0x3a8aba4f,0x2e46bba8,0xb89bb8ec,0x3a6d36d7,0x3af6367c,0x38c4bb3b,0x37e3bb50,
0xb81db9ed,0xba0fb89b,0xbadd395f,0xb93a3a8a,0x30b23b88,0x38ec39cb,0x3beab564,0x3a4fb984,0x33c6bbfe,0xb732bac2,0xbbc3aa48,0xbb253848,
0x3b64361f,0x3bb635c2,0x361fbb64,0x3444bb77,0xbb64b61f,0xbbfab179,0xb61f3b64,0xacb53be2,0x3b64361f,0x3bf1a648,0x361fbb64,0xafd6bbff,
0xbb64b61f,0xbb993303,0xb61f3b64,0x35053bce,0x3bea3564,0x3bff3505,0x30b2bb88,0x2648bb99,0xbbc32a48,0xbac23444,0x33c63bfe,0x38483bb6,
0x3a6db6d7,0x367cba0f,0xb8c4bb3b,0xbb50b93a,0xb81d39ed,0x31793bf1,0x3add395f,0x3be22fd6,0x3bf634a5,0x3bce3444,0xae46bba8,0xb303bbb6,
0xb913378b,0xb5c2393a,0x3a2f3b0e,0x3b773a0f,0xae46bba8,0xb89bbbf1,0xbbf6b4a5,0xba8a2fd6,0x3a2f3b0e,0x3bff3732,0x3913b78b,0xa648bb25,
0x3b8833c6,0x3b253303,0xb564bbc3,0xb732bbce,0xaa483a6d,0x34443b50,0x3bfe38c4,0x3bb6367c,0xbb3bbadd,0xbbfab89b,0xb6d7381d,0x2cb53a8a,
0x39edb0b2,0x2fd6b984,0xb95fbbea,0xbbf1b9cb,0x3aa7323e,0x3a0f3179,0xb872bbd9,0xb93abbe2,0x38723bd9,0x3a4f3bff,0x3aa7323e,0x38eca648,
0xbaa7b23e,0xb7323303,0x38723bd9,0x3b253bce,0xb872bbd9,0xbbb6bb50,0xbaa7b23e,0xb444367c,0x395f30b2,0x389b2fd6,0xb9edbbea,0xba8abbf1,
0x3b883bc3,0x3bff3b25,0x3564b3c6,0x2648b732,0x2a4838c4,0x38483af6,0x3bfe3a6d,0x3ac237e3,0xbb3bb81d,0xb67c2cb5,0x36d73add,0x3b503bfa,
0x378b2e46,0x35c22cb5,0xbb0ebbf6,0xbb77bbfa,0x3ba83a2f,0x3a8a38ec,0xb4a5b913,0xb89bba4f,0x3b0e3bf6,0x3bff3b99,0x378b2e46,0xa648b505,
0x34a53913,0x3ac23bb6,0x3ba83a2f,0x38483444,0x33c62a48,0x2fd62648,0xbbc3bbfe,0xbbf1bbff,0x38c436d7,0x35053303,0xba6dbb3b,0xbb99bbce,
0x3add39ed,0x37e3367c,0xb81db95f,0xbaf6bb50,0x3bea3b88,0x393a389b,0xb0b2b564,0xba0fba8a,0x3c003c00,0xbbf1bbff,0,0x2fd62648,
0x3c003c00,0xbb99bbce,0,0x35053303,0x3c003c00,0xbaf6bb50,0,0x37e3367c,0x3c003c00,0xba0fba8a,0,0x393a389b,
0x3bc33bfe,0xbb77bbfa,0xb3c6aa48,0x35c22cb5,0x3a6d3b3b,0xb89bba4f,0xb8c4b6d7,0x3a8a38ec,0x381d395f,0xa648b505,0xbaddb9ed,0x3bff3b99,
0x30b23564,0x38483444,0xbbeabb88,0x3ac23bb6,0x3b0e3bf6,0xba8abbf1,0xb78bae46,0x389b2fd6,0x34a53913,0x2648b732,0xbba8ba2f,0x3bff3b25,
0xb78bae46,0x3ac237e3,0xbb0ebbf6,0x38483af6,0xbba8ba2f,0x3b503bfa,0xb4a5b913,0xb67c2cb5,0x39ed3bea,0xb93abbe2,0xb95fb0b2,0x3a0f3179,
0xb56433c6,0x38eca648,0xbb88bbc3,0x3a4f3bff,0xbbfeba6d,0x3b253bce,0xaa48b8c4,0xb7323303,0xb6d7badd,0xb444367c,0x3b3b381d,0xbbb6bb50,
0x38723bd9,0xb732bbce,0xbaa7b23e,0x3b253303,0xbaa7b23e,0x3bb6367c,0xb872bbd9,0x34443b50,0xb872bbd9,0x2cb53a8a,0x3aa7323e,0xbbfab89b,
0x3aa7323e,0xbbf1b9cb,0x38723bd9,0x2fd6b984,0x35643bc3,0xb303bbb6,0xbb88b3c6,0x3bce3444,0xbbfeb8c4,0x3b773a0f,0x2a48ba6d,0xb5c2393a,
0x36d7b81d,0xba8a2fd6,0x3b3b3add,0xb89bbbf1,0x395f3bea,0xa648bb25,0xb9ed30b2,0x3bff3732,0x2e463ba8,0x2648bb99,0xbbf6b4a5,0x3bff3505,
0xba2fbb0e,0x38483bb6,0x3913b78b,0xbac23444,0x3bf634a5,0xbb50b93a,0x2e463ba8,0x367cba0f,0xb913378b,0x3be22fd6,0xba2fbb0e,0x31793bf1,
0xb0b23b88,0x3444bb77,0xbbeab564,0x3bb635c2,0xb3c6bbfe,0xacb53be2,0x3bc3aa48,0xbbfab179,0x38c43b3b,0xafd6bbff,0xba6d36d7,0x3bf1a648,
0xbaddb95f,0x35053bce,0x381db9ed,0xbb993303,0xb61f3b64,0x37e3bb50,0xbb64b61f,0x3af6367c,0x361fbb64,0xb93a3a8a,0x3b64361f,0xba0fb89b,
0xb61f3b64,0x3a4fb984,0xbb64b61f,0x38ec39cb,0x361fbb64,0xbb253848,0x3b64361f,0xb732bac2,0xb8c43b3b,0x3984bb25,0xba6db6d7,0x39cb3732,
0x3addb95f,0xbbce37e3,0x381d39ed,0xb303baf6,0xbbea3564,0x3b772cb5,0xb0b2bb88,0xb5c23bfa,0x3bc32a48,0xb89bb8ec,0xb3c63bfe,0x3a8aba4f,
0xba2f3b0e,0x3ac2baf6,0xb913b78b,0x384837e3,0x3bf6b4a5,0xbb502cb5,0xae463ba8,0x367cbbfa,0xb913b78b,0x31793a4f,0x3a2fbb0e,0xbbe238ec,
0xae463ba8,0x39cbbb99,0xbbf634a5,0x39843505,0xbb3b3add,0x3b99bac2,0xb6d7b81d,0x35053848,0x39ed30b2,0xb7e3b5c2,0xb95f3bea,0x3af6bb77,
0x3564bbc3,0xba0f3be2,0x3b88b3c6,0xb93ab179,0xbbfe38c4,0x3a4fa648,0xaa48ba6d,0xb8ec3bff,0xbbd93aa7,0x3bfaba8a,0xb23eb872,0x2cb5389b,
0x323e3872,0x2fd6b9cb,0xbbd93aa7,0x3bf1b984,0x3bd9baa7,0xbb993848,0x323e3872,0x3505bac2,0xb23eb872,0xb7e33b77,0x3bd9baa7,0xbaf635c2,
0xbbfe3a6d,0x3be2ba4f,0x2a48b8c4,0xb17938ec,0xb6d73add,0x3984bb99,0xbb3b381d,0x39cbb505,0x395fb0b2,0xb303b444,0xb9ed3bea,0x3bcebbb6,
0x3b88bbc3,0xbb77393a,0x356433c6,0x35c2ba0f,0xbba83a2f,0x3b50ba0f,0x34a5b913,0xb67c393a,0xbb0e3bf6,0x3be2bbf1,0xb78b2e46,0x31792fd6,
0xb4a53913,0x39cbbb25,0xbba83a2f,0x3984b732,0x378bae46,0x3303b7e3,0xbb0e3bf6,0x3bcebaf6,0xbadd39ed,0x3a4fb9cb,0x381db95f,0xb8ec3984,
0xbbea3b88,0x3b25bac2,0x30b2b564,0xb7323848,0xbbc33bfe,0x3bb6bb77,0xb3c62a48,0xb44435c2,0xba6d3b3b,0x3bfabbe2,0xb8c436d7,0xacb53179,
0xb9a839a8,0x38ecb984,0x39a8b9a8,0xba4f39cb,0xb9a839a8,0x3732b848,0x39a8b9a8,0xbb253ac2,0xb9a839a8,0x3444b5c2,0x39a8b9a8,0xbbb63b77,
0xb9a839a8,0x2cb5b179,0x39a8b9a8,0xbbfa3be2,0xb81d395f,0x367cb93a,0x3addb9ed,0xbb503a0f,0xb0b23564,0xb179afd6,0x3beabb88,0xbbe23bf1,
0x33c6aa48,0xb9843732,0x3bc3bbfe,0xb9cb3b25,0x38c4b6d7,0xbbce3af6,0x3a6dbb3b,0xb30337e3,0xb4a53913,0x3179b8ec,0x3ba8ba2f,0xbbe23a4f,
0x378bae46,0xb9cb3505,0x3b0ebbf6,0xb9843b99,0x3ba8ba2f,0xbbce3bb6,0x34a5b913,0x33033444,0x3b0ebbf6,0xb5c23a0f,0xb78b2e46,0x3b77b93a,
0xaa4838c4,0xacb5b89b,0x3bfeba6d,0xbbfa3a8a,0x3b3bb81d,0xbbf13984,0x36d7badd,0xafd639cb,0x39edbbea,0xb5053ac2,0xb95f30b2,0x3b99b848,
0xb564b3c6,0x3af6b5c2,0xbb883bc3,0x37e3bb77,0x323e3872,0xb505b848,0x3bd9baa7,0xbb993ac2,0x3bd9baa7,0xbaf63b77,0xb23eb872,0x37e335c2,
0xb23eb872,0x393a3179,0xbbd93aa7,0x3a0fbbe2,0xbbd93aa7,0x38ecbbff,0x323e3872,0xba4f2648,0x36d7381d,0xb848b7e3,0x3b3bbadd,0xbac23af6,
0x395fbbea,0xb67c3bfa,0xb9edb0b2,0x3b50acb5,0xbb8833c6,0x3be2b8ec,0xb5643bc3,0xb179ba4f,0x2a483a6d,0xb984b505,0x3bfeb8c4,0xb9cb3b99,
0x3913378b,0xb9cbb732,0x3a2fbb0e,0xb9843b25,0x2e46bba8,0x33033af6,0xbbf634a5,0x3bceb7e3,0xba2f3b0e,0x35c2bbfa,0x3913378b,0xbb77acb5,
0x3bf6b4a5,0xba8a3a4f,0x2e46bba8,0x389b38ec,0x3a6d36d7,0xbaf6b67c,0x38c4bb3b,0xb7e33b50,0xb81db9ed,0x3a0f389b,0xbadd395f,0x393aba8a,
0x30b23b88,0xb8ecb9cb,0x3beab564,0xba4f3984,0x33c6bbfe,0x37323ac2,0xbbc3aa48,0x3b25b848,0x3b64361f,0xbbb6b5c2,0x361fbb64,0xb4443b77,
0xbb64b61f,0x3bfa3179,0xb61f3b64,0x2cb5bbe2,0x3b64361f,0xbbf12648,0x361fbb64,0x2fd63bff,0xbb64b61f,0x3b99b303,0xb61f3b64,0xb505bbce,
0x3bea3564,0xbbffb505,0x30b2bb88,0xa6483b99,0xbbc32a48,0x3ac2b444,0x33c63bfe,0xb848bbb6,0x3a6db6d7,0xb67c3a0f,0xb8c4bb3b,0x3b50393a,
0xb81d39ed,0xb179bbf1,0x3add395f,0xbbe2afd6,0x3bf634a5,0xbbceb444,0xae46bba8,0x33033bb6,0xb913378b,0x35c2b93a,0x3a2f3b0e,0xbb77ba0f,
0xae46bba8,0x389b3bf1,0xbbf6b4a5,0x3a8aafd6,0x3a2f3b0e,0xbbffb732,0x3913b78b,0x26483b25,0x3b8833c6,0xbb25b303,0xb564bbc3,0x37323bce,
0xaa483a6d,0xb444bb50,0x3bfe38c4,0xbbb6b67c,0xbb3bbadd,0x3bfa389b,0xb6d7381d,0xacb5ba8a,0x39edb0b2,0xafd63984,0xb95fbbea,0x3bf139cb,
0x3aa7323e,0xba0fb179,0xb872bbd9,0x393a3be2,0x38723bd9,0xba4fbbff,0x3aa7323e,0xb8ec2648,0xbaa7b23e,0x3732b303,0x38723bd9,0xbb25bbce,
0xb872bbd9,0x3bb63b50,0xbaa7b23e,0x3444b67c,0x395f30b2,0xb89bafd6,0xb9edbbea,0x3a8a3bf1,0x3b883bc3,0xbbffbb25,0x3564b3c6,0xa6483732,
0x2a4838c4,0xb848baf6,0x3bfe3a6d,0xbac2b7e3,0xbb3bb81d,0x367cacb5,0x36d73add,0xbb50bbfa,0x378b2e46,0xb5c2acb5,0xbb0ebbf6,0x3b773bfa,
0x3ba83a2f,0xba8ab8ec,0xb4a5b913,0x389b3a4f,0x3b0e3bf6,0xbbffbb99,0x378b2e46,0x26483505,0x34a53913,0xbac2bbb6,0x3ba83a2f,0xb848b444,
0x33c62a48,0xafd6a648,0xbbc3bbfe,0x3bf13bff,0x38c436d7,0xb505b303,0xba6dbb3b,0x3b993bce,0x3add39ed,0xb7e3b67c,0xb81db95f,0x3af63b50,
0x3bea3b88,0xb93ab89b,0xb0b2b564,0x3a0f3a8a,0x3c003c00,0x38ec3984,0,0xba4fb9cb,0x3c003c00,0x37323848,0,0xbb25bac2,
0x3c003c00,0x344435c2,0,0xbbb6bb77,0x3c003c00,0x2cb53179,0,0xbbfabbe2,0xb3c6aa48,0xbb50ba0f,0xbbc3bbfe,0xb67cb93a,
0xb8c4b6d7,0xbbe2bbf1,0xba6dbb3b,0x3179afd6,0xbaddb9ed,0xb9cbbb25,0xb81db95f,0x39843732,0xbbeabb88,0xb303b7e3,0xb0b2b564,0x3bce3af6,
0xbb0ebbf6,0xb179b8ec,0x378b2e46,0x3be23a4f,0xb4a5b913,0x39cb3505,0x3ba83a2f,0x39843b99,0x378b2e46,0x3bce3bb6,0x3b0e3bf6,0xb3033444,
0x3ba83a2f,0x35c23a0f,0x34a53913,0xbb77b93a,0x395f30b2,0x3bfa3a8a,0x39ed3bea,0xacb5389b,0x3b883bc3,0x2fd639cb,0xb56433c6,0xbbf1b984,
0x2a4838c4,0xbb99b848,0xbbfeba6d,0xb505bac2,0xbb3bb81d,0xb7e3bb77,0xb6d7badd,0x3af635c2,0x38723bd9,0xb5053848,0xbaa7b23e,0xbb99bac2,
0xbaa7b23e,0xbaf6bb77,0xb872bbd9,0x37e3b5c2,0xb872bbd9,0x393ab179,0x3aa7323e,0x3a0f3be2,0x3aa7323e,0x38ec3bff,0x38723bd9,0xba4fa648,
0xbb88b3c6,0xbac2baf6,0xb564bbc3,0x3848b7e3,0x2a48ba6d,0x3b502cb5,0x3bfe38c4,0x367c3bfa,0x3b3b3add,0xb1793a4f,0xb6d7381d,0xbbe2b8ec,
0xb9ed30b2,0xb9cbbb99,0xb95fbbea,0x3984b505,0xae46bba8,0x39cbb732,0x3bf634a5,0x39843b25,0x3a2f3b0e,0xb3033af6,0xb913378b,0xbbceb7e3,
0xbbf6b4a5,0xb5c2bbfa,0xae46bba8,0x3b77acb5,0x3913b78b,0x3a8a3a4f,0x3a2f3b0e,0xb89b38ec,0x3bea3564,0x37e33b50,0xb0b23b88,0xbaf6367c,
0xbbc32a48,0xb93aba8a,0xb3c6bbfe,0x3a0fb89b,0x3a6db6d7,0x3a4f3984,0x38c43b3b,0xb8ec39cb,0xb81d39ed,0xbb25b848,0xbaddb95f,0x3732bac2,
0xb61f3b64,0xbbb635c2,0xbb64b61f,0xb444bb77,0x361fbb64,0x3bfab179,0x3b64361f,0x2cb53be2,0xb61f3b64,0xbbf1a648,0xbb64b61f,0x2fd6bbff,
0x361fbb64,0x3b993303,0x3b64361f,0xb5053bce,0xba6db6d7,0xa648bb99,0x38c4bb3b,0x3bffb505,0x381d39ed,0xb8483bb6,0xbadd395f,0xbac2b444,
0xb0b2bb88,0x3b50b93a,0x3beab564,0x367c3a0f,0xb3c63bfe,0xbbe22fd6,0xbbc3aa48,0x3179bbf1,0x3a2fbb0e,0x3bceb444,0x3913378b,0xb3033bb6,
0xbbf634a5,0xb5c2b93a,0x2e46bba8,0x3b77ba0f,0x3913378b,0xb89b3bf1,0xba2f3b0e,0xba8aafd6,0x2e46bba8,0x3bffb732,0x3bf6b4a5,0xa6483b25,
0x36d7381d,0xb7323bce,0xbb3b3add,0xbb253303,0x395fbbea,0x3bb6b67c,0x39ed30b2,0xb4443b50,0xbb8833c6,0x2cb5ba8a,0x3564bbc3,0x3bfab89b,
0x2a483a6d,0xbbf139cb,0xbbfe38c4,0xafd6b984,0xbbd93aa7,0xba0f3179,0xb23eb872,0x393abbe2,0x323e3872,0xba4f3bff,0xbbd93aa7,0xb8eca648,
0x3bd9baa7,0x37323303,0x323e3872,0xbb253bce,0xb23eb872,0x3bb6bb50,0x3bd9baa7,0x3444367c,0x2a48b8c4,0x3a8abbf1,0x3bfeba6d,0x389bafd6,
0xbb3b381d,0xa648b732,0x36d7badd,0x3bffbb25,0xb9ed3bea,0xbac237e3,0xb95f30b2,0x3848baf6,0x356433c6,0xbb503bfa,0xbb883bc3,0xb67cacb5,
0x3ba8ba2f,0x35c2acb5,0xb4a53913,0xbb773bfa,0x3b0ebbf6,0x3a8ab8ec,0x378bae46,0xb89b3a4f,0x34a5b913,0x3bffbb99,0x3ba8ba2f,0xa6483505,
0xb78b2e46,0x3ac2bbb6,0x3b0ebbf6,0x3848b444,0xb81d395f,0xbbf13bff,0xbadd39ed,0xafd62648,0xb0b23564,0xbb993bce,0xbbea3b88,0xb5053303,
0x33c6aa48,0xbaf63b50,0xbbc33bfe,0xb7e3367c,0x38c4b6d7,0xba0f3a8a,0xba6d3b3b,0xb93a389b,0xb9a839a8,0x2fd6a648,0x39a8b9a8,0x3bf1bbff,
0xb9a839a8,0x3505b303,0x39a8b9a8,0x3b99bbce,0xb9a839a8,0x37e3b67c,0x39a8b9a8,0x3af6bb50,0xb9a839a8,0x393ab89b,0x39a8b9a8,0x3a0fba8a,
0x3addb9ed,0x3b77bbfa,0x381db95f,0xb5c22cb5,0x3beabb88,0x389bba4f,0x30b2b564,0xba8a38ec,0x3bc3bbfe,0x2648b505,0xb3c62a48,0xbbff3b99,
0x3a6dbb3b,0xb8483444,0xb8c436d7,0xbac23bb6,0x34a5b913,0xb89b2fd6,0xbba83a2f,0xba8a3bf1,0xb78b2e46,0xbbff3b25,0xbb0e3bf6,0x26483732,
0xbba83a2f,0xb8483af6,0xb4a53913,0x3ac2b7e3,0xbb0e3bf6,0x367c2cb5,0x378bae46,0x3b50bbfa,0xbbfe3a6d,0xb93a3be2,0xaa4838c4,0x3a0fb179,
0xb6d73add,0x38ec2648,0x3b3bb81d,0x3a4fbbff,0x395fb0b2,0x3b25bbce,0x39edbbea,0xb732b303,0x3b88bbc3,0xb444b67c,0xb564b3c6,0xbbb63b50,
0x323e3872,0x3b25b303,0x3bd9baa7,0x3732bbce,0x3bd9baa7,0x3444bb50,0xb23eb872,0xbbb6367c,0xb23eb872,0xbbfa389b,0xbbd93aa7,0xacb53a8a,
0xbbd93aa7,0x2fd63984,0x323e3872,0x3bf1b9cb,0x3b3bbadd,0x3303bbb6,0xb6d7b81d,0xbbce3444,0xb9edb0b2,0xbb773a0f,0xb95f3bea,0x35c2393a,
0xb5643bc3,0x3a8a2fd6,0x3b88b3c6,0x389bbbf1,0x3bfeb8c4,0x2648bb25,0xaa48ba6d,0xbbff3732,0xb913b78b,0xbbff3505,0xba2f3b0e,0x26483b99,
0xae463ba8,0x3ac23444,0x3bf6b4a5,0x3848bbb6,0x3a2fbb0e,0xb67cba0f,0xb913b78b,0xbb50393a,0xbbf634a5,0xb1793bf1,0xae463ba8,0x3be2afd6,
0xb8c43b3b,0x34443b77,0x3a6d36d7,0x3bb6b5c2,0x3addb95f,0xacb5bbe2,0xb81db9ed,0xbbfa3179,0xbbea3564,0xafd63bff,0x30b23b88,0x3bf12648,
0x3bc32a48,0x3505bbce,0x33c6bbfe,0xbb99b303,0x3b64361f,0x3af6b67c,0x361fbb64,0xb7e3bb50,0xbb64b61f,0xba0f389b,0xb61f3b64,0x393a3a8a,
0x3b64361f,0x38ecb9cb,0x361fbb64,0xba4fb984,0xbb64b61f,0xb7323ac2,0xb61f3b64,0x3b253848,0x30b2bb88,0xb984bb25,0xbbeab564,0xb9cb3732,
0x33c63bfe,0x3bce37e3,0x3bc3aa48,0x3303baf6,0xb8c4bb3b,0xbb772cb5,0xba6d36d7,0x35c23bfa,0x3add395f,0x389bb8ec,0x381db9ed,0xba8aba4f,
0xbbf6b4a5,0xb84837e3,0x2e463ba8,0x3ac23af6,0x3913b78b,0xb67cbbfa,0xba2fbb0e,0xbb50acb5,0x2e463ba8,0x3be238ec,0x3bf634a5,0x3179ba4f,
0xba2fbb0e,0xb9843505,0xb913378b,0x39cb3b99,0x35643bc3,0x3b993ac2,0x3b8833c6,0x3505b848,0xbbfeb8c4,0xb7e335c2,0xaa483a6d,0x3af63b77,
0x36d7b81d,0xba0fbbe2,0xbb3bbadd,0xb93a3179,0x395f3bea,0x3a4f2648,0x39edb0b2,0xb8ecbbff,0x3aa7323e,0x2cb5b89b,0xb872bbd9,0xbbfaba8a,
0x38723bd9,0x3bf13984,0x3aa7323e,0xafd6b9cb,0xbaa7b23e,0x35053ac2,0x38723bd9,0x3b993848,0xb872bbd9,0xbaf6b5c2,0xbaa7b23e,0x37e33b77,
0xb9edbbea,0xbbe2ba4f,0xb95fb0b2,0x317938ec,0x3564b3c6,0xb984bb99,0xbb88bbc3,0xb9cbb505,0x3bfe3a6d,0x3303b444,0xaa48b8c4,0xbbcebbb6,
0x36d73add,0x3b77393a,0x3b3b381d,0xb5c2ba0f,0xb78bae46,0x367c393a,0x3b0e3bf6,0x3b503a0f,0xbba8ba2f,0xb1792fd6,0x34a53913,0x3be23bf1,
0xbb0ebbf6,0xb984b732,0xb78bae46,0x39cb3b25,0xb4a5b913,0xbbcebaf6,0xbba8ba2f,0x330337e3,0x3bc33bfe,0x3a4f39cb,0x33c62a48,0xb8ecb984,
0x3a6d3b3b,0x3b253ac2,0x38c436d7,0xb732b848,0x381d395f,0x3bb63b77,0x3add39ed,0xb444b5c2,0x30b23564,0x3bfa3be2,0x3bea3b88,0xacb5b179,
0x3c003c00,0xb8ecb984,0,0x3a4f39cb,0x3c003c00,0xb732b848,0,0x3b253ac2,0x3c003c00,0xb444b5c2,0,0x3bb63b77,
0x3c003c00,0xacb5b179,0,0x3bfa3be2,0xb3c6aa48,0x3b503a0f,0xbbc3bbfe,0x367c393a,0xb8c4b6d7,0x3be23bf1,0xba6dbb3b,0xb1792fd6,
0xbaddb9ed,0x39cb3b25,0xb81db95f,0xb984b732,0xbbeabb88,0x330337e3,0xb0b2b564,0xbbcebaf6,0xbb0ebbf6,0x317938ec,0x378b2e46,0xbbe2ba4f,
0xb4a5b913,0xb9cbb505,0x3ba83a2f,0xb984bb99,0x378b2e46,0xbbcebbb6,0x3b0e3bf6,0x3303b444,0x3ba83a2f,0xb5c2ba0f,0x34a53913,0x3b77393a,
0x395f30b2,0xbbfaba8a,0x39ed3bea,0x2cb5b89b,0x3b883bc3,0xafd6b9cb,0xb56433c6,0x3bf13984,0x2a4838c4,0x3b993848,0xbbfeba6d,0x35053ac2,
0xbb3bb81d,0x37e33b77,0xb6d7badd,0xbaf6b5c2,0x38723bd9,0x3505b848,0xbaa7b23e,0x3b993ac2,0xbaa7b23e,0x3af63b77,0xb872bbd9,0xb7e335c2,
0xb872bbd9,0xb93a3179,0x3aa7323e,0xba0fbbe2,0x3aa7323e,0xb8ecbbff,0x38723bd9,0x3a4f2648,0xbb88b3c6,0x3ac23af6,0xb564bbc3,0xb84837e3,
0x2a48ba6d,0xbb50acb5,0x3bfe38c4,0xb67cbbfa,0x3b3b3add,0x3179ba4f,0xb6d7381d,0x3be238ec,0xb9ed30b2,0x39cb3b99,0xb95fbbea,0xb9843505,
0xae46bba8,0xb9cb3732,0x3bf634a5,0xb984bb25,0x3a2f3b0e,0x3303baf6,0xb913378b,0x3bce37e3,0xbbf6b4a5,0x35c23bfa,0xae46bba8,0xbb772cb5,
0x3913b78b,0xba8aba4f,0x3a2f3b0e,0x389bb8ec,0x3bea3564,0xb7e3bb50,0xb0b23b88,0x3af6b67c,0xbbc32a48,0x393a3a8a,0xb3c6bbfe,0xba0f389b,
0x3a6db6d7,0xba4fb984,0x38c43b3b,0x38ecb9cb,0xb81d39ed,0x3b253848,0xbaddb95f,0xb7323ac2,0xb61f3b64,0x3bb6b5c2,0xbb64b61f,0x34443b77,
0x361fbb64,0xbbfa3179,0x3b64361f,0xacb5bbe2,0xb61f3b64,0x3bf12648,0xbb64b61f,0xafd63bff,0x361fbb64,0xbb99b303,0x3b64361f,0x3505bbce,
0xba6db6d7,0x26483b99,0x38c4bb3b,0xbbff3505,0x381d39ed,0x3848bbb6,0xbadd395f,0x3ac23444,0xb0b2bb88,0xbb50393a,0x3beab564,0xb67cba0f,
0xb3c63bfe,0x3be2afd6,0xbbc3aa48,0xb1793bf1,0x3a2fbb0e,0xbbce3444,0x3913378b,0x3303bbb6,0xbbf634a5,0x35c2393a,0x2e46bba8,0xbb773a0f,
0x3913378b,0x389bbbf1,0xba2f3b0e,0x3a8a2fd6,0x2e46bba8,0xbbff3732,0x3bf6b4a5,0x2648bb25,0x36d7381d,0x3732bbce,0xbb3b3add,0x3b25b303,
0x395fbbea,0xbbb6367c,0x39ed30b2,0x3444bb50,0xbb8833c6,0xacb53a8a,0x3564bbc3,0xbbfa389b,0x2a483a6d,0x3bf1b9cb,0xbbfe38c4,0x2fd63984,
0xbbd93aa7,0x3a0fb179,0xb23eb872,0xb93a3be2,0x323e3872,0x3a4fbbff,0xbbd93aa7,0x38ec2648,0x3bd9baa7,0xb732b303,0x323e3872,0x3b25bbce,
0xb23eb872,0xbbb63b50,0x3bd9baa7,0xb444b67c,0x2a48b8c4,0xba8a3bf1,0x3bfeba6d,0xb89b2fd6,0xbb3b381d,0x26483732,0x36d7badd,0xbbff3b25,
0xb9ed3bea,0x3ac2b7e3,0xb95f30b2,0xb8483af6,0x356433c6,0x3b50bbfa,0xbb883bc3,0x367c2cb5,0x3ba8ba2f,0xb5c22cb5,0xb4a53913,0x3b77bbfa,
0x3b0ebbf6,0xba8a38ec,0x378bae46,0x389bba4f,0x34a5b913,0xbbff3b99,0x3ba8ba2f,0x2648b505,0xb78b2e46,0xbac23bb6,0x3b0ebbf6,0xb8483444,
0xb81d395f,0x3bf1bbff,0xbadd39ed,0x2fd6a648,0xb0b23564,0x3b99bbce,0xbbea3b88,0x3505b303,0x33c6aa48,0x3af6bb50,0xbbc33bfe,0x37e3b67c,
0x38c4b6d7,0x3a0fba8a,0xba6d3b3b,0x393ab89b,0xb9a839a8,0xafd62648,0x39a8b9a8,0xbbf13bff,0xb9a839a8,0xb5053303,0x39a8b9a8,0xbb993bce,
0xb9a839a8,0xb7e3367c,0x39a8b9a8,0xbaf63b50,0xb9a839a8,0xb93a389b,0x39a8b9a8,0xba0f3a8a,0x3addb9ed,0xbb773bfa,0x381db95f,0x35c2acb5,
0x3beabb88,0xb89b3a4f,0x30b2b564,0x3a8ab8ec,0x3bc3bbfe,0xa6483505,0xb3c62a48,0x3bffbb99,0x3a6dbb3b,0x3848b444,0xb8c436d7,0x3ac2bbb6,
0x34a5b913,0x389bafd6,0xbba83a2f,0x3a8abbf1,0xb78b2e46,0x3bffbb25,0xbb0e3bf6,0xa648b732,0xbba83a2f,0x3848baf6,0xb4a53913,0xbac237e3,
0xbb0e3bf6,0xb67cacb5,0x378bae46,0xbb503bfa,0xbbfe3a6d,0x393abbe2,0xaa4838c4,0xba0f3179,0xb6d73add,0xb8eca648,0x3b3bb81d,0xba4f3bff,
0x395fb0b2,0xbb253bce,0x39edbbea,0x37323303,0x3b88bbc3,0x3444367c,0xb564b3c6,0x3bb6bb50,0x323e3872,0xbb253303,0x3bd9baa7,0xb7323bce,
0x3bd9baa7,0xb4443b50,0xb23eb872,0x3bb6b67c,0xb23eb872,0x3bfab89b,0xbbd93aa7,0x2cb5ba8a,0xbbd93aa7,0xafd6b984,0x323e3872,0xbbf139cb,
0x3b3bbadd,0xb3033bb6,0xb6d7b81d,0x3bceb444,0xb9edb0b2,0x3b77ba0f,0xb95f3bea,0xb5c2b93a,0xb5643bc3,0xba8aafd6,0x3b88b3c6,0xb89b3bf1,
0x3bfeb8c4,0xa6483b25,0xaa48ba6d,0x3bffb732,0xb913b78b,0x3bffb505,0xba2f3b0e,0xa648bb99,0xae463ba8,0xbac2b444,0x3bf6b4a5,0xb8483bb6,
0x3a2fbb0e,0x367c3a0f,0xb913b78b,0x3b50b93a,0xbbf634a5,0x3179bbf1,0xae463ba8,0xbbe22fd6,0xb8c43b3b,0xb444bb77,0x3a6d36d7,0xbbb635c2,
0x3addb95f,0x2cb53be2,0xb81db9ed,0x3bfab179,0xbbea3564,0x2fd6bbff,0x30b23b88,0xbbf1a648,0x3bc32a48,0xb5053bce,0x33c6bbfe,0x3b993303,
0x3b64361f,0xbaf6367c,0x361fbb64,0x37e33b50,0xbb64b61f,0x3a0fb89b,0xb61f3b64,0xb93aba8a,0x3b64361f,0xb8ec39cb,0x361fbb64,0x3a4f3984,
0xbb64b61f,0x3732bac2,0xb61f3b64,0xbb25b848,0x30b2bb88,0x39843b25,0xbbeab564,0x39cbb732,0x33c63bfe,0xbbceb7e3,0x3bc3aa48,0xb3033af6,
0xb8c4bb3b,0x3b77acb5,0xba6d36d7,0xb5c2bbfa,0x3add395f,0xb89b38ec,0x381db9ed,0x3a8a3a4f,0xbbf6b4a5,0x3848b7e3,0x2e463ba8,0xbac2baf6,
0x3913b78b,0x367c3bfa,0xba2fbb0e,0x3b502cb5,0x2e463ba8,0xbbe2b8ec,0x3bf634a5,0xb1793a4f,0xba2fbb0e,0x3984b505,0xb913378b,0xb9cbbb99,
0x35643bc3,0xbb99bac2,0x3b8833c6,0xb5053848,0xbbfeb8c4,0x37e3b5c2,0xaa483a6d,0xbaf6bb77,0x36d7b81d,0x3a0f3be2,0xbb3bbadd,0x393ab179,
0x395f3bea,0xba4fa648,0x39edb0b2,0x38ec3bff,0x3aa7323e,0xacb5389b,0xb872bbd9,0x3bfa3a8a,0x38723bd9,0xbbf1b984,0x3aa7323e,0x2fd639cb,
0xbaa7b23e,0xb505bac2,0x38723bd9,0xbb99b848,0xb872bbd9,0x3af635c2,0xbaa7b23e,0xb7e3bb77,0xb9edbbea,0x3be23a4f,0xb95fb0b2,0xb179b8ec,
0x3564b3c6,0x39843b99,0xbb88bbc3,0x39cb3505,0x3bfe3a6d,0xb3033444,0xaa48b8c4,0x3bce3bb6,0x36d73add,0xbb77b93a,0x3b3b381d,0x35c23a0f,
0xb78bae46,0xb67cb93a,0x3b0e3bf6,0xbb50ba0f,0xbba8ba2f,0x3179afd6,0x34a53913,0xbbe2bbf1,0xbb0ebbf6,0x39843732,0xb78bae46,0xb9cbbb25,
0xb4a5b913,0x3bce3af6,0xbba8ba2f,0xb303b7e3,0x3bc33bfe,0xba4fb9cb,0x33c62a48,0x38ec3984,0x3a6d3b3b,0xbb25bac2,0x38c436d7,0x37323848,
0x381d395f,0xbbb6bb77,0x3add39ed,0x344435c2,0x30b23564,0xbbfabbe2,0x3bea3b88,0x2cb53179,0x3c003c00,0xafd6a648,0,0xbbf1bbff,
0x3c003c00,0xb505b303,0,0xbb99bbce,0x3c003c00,0xb7e3b67c,0,0xbaf6bb50,0x3c003c00,0xb93ab89b,0,0xba0fba8a,
0xbbc3bbfe,0x35c22cb5,0x33c62a48,0x3b773bfa,0xba6dbb3b,0x3a8a38ec,0x38c436d7,0x389b3a4f,0xb81db95f,0x3bff3b99,0x3add39ed,0x26483505,
0xb0b2b564,0x3ac23bb6,0x3bea3b88,0xb848b444,0x3b0e3bf6,0xb89bafd6,0xb78bae46,0xba8abbf1,0x34a53913,0xbbffbb25,0xbba8ba2f,0x2648b732,
0xb78bae46,0xb848baf6,0xbb0ebbf6,0x3ac237e3,0xbba8ba2f,0x367cacb5,0xb4a5b913,0x3b503bfa,0xb9edbbea,0x3a0f3179,0x395f30b2,0x393a3be2,
0x3564b3c6,0x3a4f3bff,0x3b883bc3,0xb8ec2648,0x3bfe3a6d,0xb7323303,0x2a4838c4,0xbb25bbce,0x36d73add,0xbbb6bb50,0xbb3bb81d,0x3444b67c,
0x38723bd9,0xbb25b303,0xbaa7b23e,0xb732bbce,0xbaa7b23e,0xb444bb50,0xb872bbd9,0x3bb6367c,0xb872bbd9,0x3bfa389b,0x3aa7323e,0x2cb53a8a,
0x3aa7323e,0xafd63984,0x38723bd9,0xbbf1b9cb,0xb564bbc3,0x3bce3444,0x3b8833c6,0x33033bb6,0x3bfe38c4,0xb5c2393a,0xaa483a6d,0xbb77ba0f,
0xb6d7381d,0xb89bbbf1,0xbb3bbadd,0x3a8aafd6,0xb95fbbea,0x3bff3732,0x39edb0b2,0x26483b25,0x2e463ba8,0xbbffb505,0xbbf6b4a5,0x2648bb99,
0xba2fbb0e,0x3ac2b444,0x3913b78b,0x38483bb6,0x3bf634a5,0xb67c3a0f,0x2e463ba8,0xbb50b93a,0xb913378b,0xb179bbf1,0xba2fbb0e,0x3be22fd6,
0x30b2bb88,0x3bb635c2,0x3bea3564,0xb4443b77,0x33c63bfe,0xbbfab179,0xbbc32a48,0x2cb5bbe2,0xb8c4bb3b,0x3bf1a648,0x3a6db6d7,0x2fd63bff,
0x3add395f,0xbb993303,0xb81d39ed,0xb505bbce,0xb61f3b64,0xbaf6b67c,0xbb64b61f,0x37e3bb50,0x361fbb64,0x3a0f389b,0x3b64361f,0xb93a3a8a,
0xb61f3b64,0xb8ecb9cb,0xbb64b61f,0x3a4fb984,0x361fbb64,0x37323ac2,0x3b64361f,0xbb253848,0x38c4bb3b,0x39cb3732,0x3a6d36d7,0xb9843b25,
0xbadd395f,0xb303baf6,0xb81db9ed,0x3bceb7e3,0x3beab564,0xb5c23bfa,0x30b23b88,0xbb77acb5,0xbbc3aa48,0x3a8aba4f,0x33c6bbfe,0x389b38ec,
0xba2f3b0e,0xb848b7e3,0xb913b78b,0x3ac2baf6,0x3bf6b4a5,0xb67c3bfa,0xae463ba8,0xbb502cb5,0xb913b78b,0x3be2b8ec,0x3a2fbb0e,0x31793a4f,
0xae463ba8,0xb984b505,0xbbf634a5,0x39cbbb99,0x3b3bbadd,0x35053848,0x36d7381d,0xbb993ac2,0xb9edb0b2,0x3af6bb77,0x395fbbea,0x37e335c2,
0xb5643bc3,0xb93ab179,0xbb8833c6,0x3a0fbbe2,0x3bfeb8c4,0xb8ec3bff,0x2a483a6d,0xba4f2648,0xbbd93aa7,0xacb5b89b,0xb23eb872,0x3bfaba8a,
0x323e3872,0xbbf13984,0xbbd93aa7,0x2fd6b9cb,0x3bd9baa7,0xb5053ac2,0x323e3872,0xbb993848,0xb23eb872,0x3af6b5c2,0x3bd9baa7,0xb7e33b77,
0x3bfeba6d,0xb17938ec,0xaa4838c4,0xbbe23a4f,0x36d7badd,0x39cbb505,0x3b3bb81d,0xb9843b99,0xb95f30b2,0x3bcebbb6,0x39edbbea,0x33033444,
0xbb883bc3,0x35c2ba0f,0xb564b3c6,0x3b77b93a,0xbba83a2f,0x367cb93a,0x34a5b913,0x3b50ba0f,0xbb0e3bf6,0xb179afd6,0xb78b2e46,0x3be2bbf1,
0xb4a53913,0xb9843732,0xbba83a2f,0x39cbbb25,0x378bae46,0xbbce3af6,0xbb0e3bf6,0x3303b7e3,0x3addb9ed,0xb8ec3984,0xb81d395f,0xba4f39cb,
0x3beabb88,0xb7323848,0xb0b23564,0xbb253ac2,0x3bc3bbfe,0xb44435c2,0x33c6aa48,0xbbb63b77,0x3a6dbb3b,0xacb53179,0x38c4b6d7,0xbbfa3be2,
0xb9a839a8,0x3a4fb9cb,0x39a8b9a8,0x38ecb984,0xb9a839a8,0x3b25bac2,0x39a8b9a8,0x3732b848,0xb9a839a8,0x3bb6bb77,0x39a8b9a8,0x3444b5c2,
0xb9a839a8,0x3bfabbe2,0x39a8b9a8,0x2cb5b179,0x381db95f,0xbb503a0f,0xbadd39ed,0xb67c393a,0x30b2b564,0xbbe23bf1,0xbbea3b88,0x31792fd6,
0xb3c62a48,0xb9cb3b25,0xbbc33bfe,0x3984b732,0xb8c436d7,0xb30337e3,0xba6d3b3b,0x3bcebaf6,0xb4a53913,0x3be2ba4f,0x3ba8ba2f,0x3179b8ec,
0x378bae46,0x3984bb99,0x3b0ebbf6,0xb9cb3505,0x3ba8ba2f,0xb303b444,0x34a5b913,0xbbce3bb6,0x3b0ebbf6,0xbb77393a,0xb78b2e46,0xb5c23a0f,
0x2a48b8c4,0xbbfa3a8a,0xbbfe3a6d,0x2cb5389b,0xbb3b381d,0xafd639cb,0xb6d73add,0x3bf1b984,0xb9ed3bea,0x3b99b848,0x395fb0b2,0x3505bac2,
0x356433c6,0x37e3bb77,0x3b88bbc3,0xbaf635c2,0x323e3872,0x3b99bac2,0x3bd9baa7,0xb505b848,0x3bd9baa7,0xb7e3b5c2,0xb23eb872,0xbaf63b77,
0xb23eb872,0xba0f3be2,0xbbd93aa7,0x393a3179,0xbbd93aa7,0x3a4fa648,0x323e3872,0x38ecbbff,0xb6d7b81d,0xbac23af6,0xbb3b3add,0x384837e3,
0xb95f3bea,0x3b50acb5,0x39ed30b2,0x367cbbfa,0x3b88b3c6,0xb179ba4f,0x3564bbc3,0xbbe238ec,0xaa48ba6d,0xb9cb3b99,0xbbfe38c4,0x39843505,
0x3913378b,0x3984bb25,0x3a2fbb0e,0xb9cbb732,0x2e46bba8,0xbbce37e3,0xbbf634a5,0x33033af6,0xba2f3b0e,0x3b772cb5,0x3913378b,0x35c2bbfa,
0x3bf6b4a5,0xb89bb8ec,0x2e46bba8,0xba8a3a4f,0xba6db6d7,0xb7e33b50,0xb8c43b3b,0x3af6367c,0x381d39ed,0x393aba8a,0x3addb95f,0xba0fb89b,
0xb0b2bb88,0xba4f3984,0xbbea3564,0x38ec39cb,0xb3c63bfe,0x3b25b848,0x3bc32a48,0xb732bac2,0x3b64361f,0x3444bb77,0x361fbb64,0xbbb6b5c2,
0xbb64b61f,0xacb53be2,0xb61f3b64,0x3bfa3179,0x3b64361f,0xafd6bbff,0x361fbb64,0xbbf12648,0xbb64b61f,0x35053bce,0xb61f3b64,0x3b99b303,
0xbbeab564,0xa6483b99,0xb0b23b88,0x3bff3505,0x3bc3aa48,0xb848bbb6,0xb3c6bbfe,0xbac23444,0xba6d36d7,0x3b50393a,0x38c43b3b,0x367cba0f,
0x381db9ed,0xbbe2afd6,0xbaddb95f,0x31793bf1,0x3bf634a5,0xb303bbb6,0xae46bba8,0xbbceb444,0xb913378b,0x3b773a0f,0x3a2f3b0e,0x35c2b93a,
0xae46bba8,0xba8a2fd6,0xbbf6b4a5,0x389b3bf1,0x3a2f3b0e,0xa648bb25,0x3913b78b,0xbbffb732,0xbb88b3c6,0x37323bce,0x35643bc3,0x3b253303,
0x2a48ba6d,0xbbb6b67c,0xbbfeb8c4,0x34443b50,0x3b3b3add,0xacb5ba8a,0x36d7b81d,0xbbfab89b,0xb9ed30b2,0x3bf139cb,0x395f3bea,0x2fd6b984,
0x3aa7323e,0xb93abbe2,0xb872bbd9,0xba0fb179,0x38723bd9,0x38eca648,0x3aa7323e,0xba4fbbff,0xbaa7b23e,0x3b253bce,0x38723bd9,0x3732b303,
0xb872bbd9,0xb444367c,0xbaa7b23e,0x3bb63b50,0xb95fb0b2,0x3a8a3bf1,0x39ed3bea,0x389b2fd6,0xbb88bbc3,0xa6483732,0xb56433c6,0x3bff3b25,
0xaa48b8c4,0xbac2b7e3,0xbbfeba6d,0x38483af6,0x3b3b381d,0xbb50bbfa,0xb6d7badd,0xb67c2cb5,0x378b2e46,0xbb77bbfa,0xbb0ebbf6,0xb5c2acb5,
0x3ba83a2f,0xb89bba4f,0xb4a5b913,0xba8ab8ec,0x3b0e3bf6,0xa648b505,0x378b2e46,0xbbffbb99,0x34a53913,0x38483444,0x3ba83a2f,0xbac2bbb6,
0xb3c6aa48,0x3bf13bff,0x3bc33bfe,0x2fd62648,0xb8c4b6d7,0x3b993bce,0x3a6d3b3b,0x35053303,0xbaddb9ed,0x3af63b50,0x381d395f,0x37e3367c,
0xbbeabb88,0x3a0f3a8a,0x30b23564,0x393a389b,0x3c003c00,0x2fd62648,0,0x3bf13bff,0x3c003c00,0x35053303,0,0x3b993bce,
0x3c003c00,0x37e3367c,0,0x3af63b50,0x3c003c00,0x393a389b,0,0x3a0f3a8a,0xbbc3bbfe,0xb5c2acb5,0x33c62a48,0xbb77bbfa,
0xba6dbb3b,0xba8ab8ec,0x38c436d7,0xb89bba4f,0xb81db95f,0xbbffbb99,0x3add39ed,0xa648b505,0xb0b2b564,0xbac2bbb6,0x3bea3b88,0x38483444,
0x3b0e3bf6,0x389b2fd6,0xb78bae46,0x3a8a3bf1,0x34a53913,0x3bff3b25,0xbba8ba2f,0xa6483732,0xb78bae46,0x38483af6,0xbb0ebbf6,0xbac2b7e3,
0xbba8ba2f,0xb67c2cb5,0xb4a5b913,0xbb50bbfa,0xb9edbbea,0xba0fb179,0x395f30b2,0xb93abbe2,0x3564b3c6,0xba4fbbff,0x3b883bc3,0x38eca648,
0x3bfe3a6d,0x3732b303,0x2a4838c4,0x3b253bce,0x36d73add,0x3bb63b50,0xbb3bb81d,0xb444367c,0x38723bd9,0x3b253303,0xbaa7b23e,0x37323bce,
0xbaa7b23e,0x34443b50,0xb872bbd9,0xbbb6b67c,0xb872bbd9,0xbbfab89b,0x3aa7323e,0xacb5ba8a,0x3aa7323e,0x2fd6b984,0x38723bd9,0x3bf139cb,
0xb564bbc3,0xbbceb444,0x3b8833c6,0xb303bbb6,0x3bfe38c4,0x35c2b93a,0xaa483a6d,0x3b773a0f,0xb6d7381d,0x389b3bf1,0xbb3bbadd,0xba8a2fd6,
0xb95fbbea,0xbbffb732,0x39edb0b2,0xa648bb25,0x2e463ba8,0x3bff3505,0xbbf6b4a5,0xa6483b99,0xba2fbb0e,0xbac23444,0x3913b78b,0xb848bbb6,
0x3bf634a5,0x367cba0f,0x2e463ba8,0x3b50393a,0xb913378b,0x31793bf1,0xba2fbb0e,0xbbe2afd6,0x30b2bb88,0xbbb6b5c2,0x3bea3564,0x3444bb77,
0x33c63bfe,0x3bfa3179,0xbbc32a48,0xacb53be2,0xb8c4bb3b,0xbbf12648,0x3a6db6d7,0xafd6bbff,0x3add395f,0x3b99b303,0xb81d39ed,0x35053bce,
0xb61f3b64,0x3af6367c,0xbb64b61f,0xb7e33b50,0x361fbb64,0xba0fb89b,0x3b64361f,0x393aba8a,0xb61f3b64,0x38ec39cb,0xbb64b61f,0xba4f3984,
0x361fbb64,0xb732bac2,0x3b64361f,0x3b25b848,0x38c4bb3b,0xb9cbb732,0x3a6d36d7,0x3984bb25,0xbadd395f,0x33033af6,0xb81db9ed,0xbbce37e3,
0x3beab564,0x35c2bbfa,0x30b23b88,0x3b772cb5,0xbbc3aa48,0xba8a3a4f,0x33c6bbfe,0xb89bb8ec,0xba2f3b0e,0x384837e3,0xb913b78b,0xbac23af6,
0x3bf6b4a5,0x367cbbfa,0xae463ba8,0x3b50acb5,0xb913b78b,0xbbe238ec,0x3a2fbb0e,0xb179ba4f,0xae463ba8,0x39843505,0xbbf634a5,0xb9cb3b99,
0x3b3bbadd,0xb505b848,0x36d7381d,0x3b99bac2,0xb9edb0b2,0xbaf63b77,0x395fbbea,0xb7e3b5c2,0xb5643bc3,0x393a3179,0xbb8833c6,0xba0f3be2,
0x3bfeb8c4,0x38ecbbff,0x2a483a6d,0x3a4fa648,0xbbd93aa7,0x2cb5389b,0xb23eb872,0xbbfa3a8a,0x323e3872,0x3bf1b984,0xbbd93aa7,0xafd639cb,
0x3bd9baa7,0x3505bac2,0x323e3872,0x3b99b848,0xb23eb872,0xbaf635c2,0x3bd9baa7,0x37e3bb77,0x3bfeba6d,0x3179b8ec,0xaa4838c4,0x3be2ba4f,
0x36d7badd,0xb9cb3505,0x3b3bb81d,0x3984bb99,0xb95f30b2,0xbbce3bb6,0x39edbbea,0xb303b444,0xbb883bc3,0xb5c23a0f,0xb564b3c6,0xbb77393a,
0xbba83a2f,0xb67c393a,0x34a5b913,0xbb503a0f,0xbb0e3bf6,0x31792fd6,0xb78b2e46,0xbbe23bf1,0xb4a53913,0x3984b732,0xbba83a2f,0xb9cb3b25,
0x378bae46,0x3bcebaf6,0xbb0e3bf6,0xb30337e3,0x3addb9ed,0x38ecb984,0xb81d395f,0x3a4fb9cb,0x3beabb88,0x3732b848,0xb0b23564,0x3b25bac2,
0x3bc3bbfe,0x3444b5c2,0x33c6aa48,0x3bb6bb77,0x3a6dbb3b,0x2cb5b179,0x38c4b6d7,0x3bfabbe2,0xb9a839a8,0xba4f39cb,0x39a8b9a8,0xb8ec3984,
0xb9a839a8,0xbb253ac2,0x39a8b9a8,0xb7323848,0xb9a839a8,0xbbb63b77,0x39a8b9a8,0xb44435c2,0xb9a839a8,0xbbfa3be2,0x39a8b9a8,0xacb53179,
0x381db95f,0x3b50ba0f,0xbadd39ed,0x367cb93a,0x30b2b564,0x3be2bbf1,0xbbea3b88,0xb179afd6,0xb3c62a48,0x39cbbb25,0xbbc33bfe,0xb9843732,
0xb8c436d7,0x3303b7e3,0xba6d3b3b,0xbbce3af6,0xb4a53913,0xbbe23a4f,0x3ba8ba2f,0xb17938ec,0x378bae46,0xb9843b99,0x3b0ebbf6,0x39cbb505,
0x3ba8ba2f,0x33033444,0x34a5b913,0x3bcebbb6,0x3b0ebbf6,0x3b77b93a,0xb78b2e46,0x35c2ba0f,0x2a48b8c4,0x3bfaba8a,0xbbfe3a6d,0xacb5b89b,
0xbb3b381d,0x2fd6b9cb,0xb6d73add,0xbbf13984,0xb9ed3bea,0xbb993848,0x395fb0b2,0xb5053ac2,0x356433c6,0xb7e33b77,0x3b88bbc3,0x3af6b5c2,
0x323e3872,0xbb993ac2,0x3bd9baa7,0x35053848,0x3bd9baa7,0x37e335c2,0xb23eb872,0x3af6bb77,0xb23eb872,0x3a0fbbe2,0xbbd93aa7,0xb93ab179,
0xbbd93aa7,0xba4f2648,0x323e3872,0xb8ec3bff,0xb6d7b81d,0x3ac2baf6,0xbb3b3add,0xb848b7e3,0xb95f3bea,0xbb502cb5,0x39ed30b2,0xb67c3bfa,
0x3b88b3c6,0x31793a4f,0x3564bbc3,0x3be2b8ec,0xaa48ba6d,0x39cbbb99,0xbbfe38c4,0xb984b505,0x3913378b,0xb9843b25,0x3a2fbb0e,0x39cb3732,
0x2e46bba8,0x3bceb7e3,0xbbf634a5,0xb303baf6,0xba2f3b0e,0xbb77acb5,0x3913378b,0xb5c23bfa,0x3bf6b4a5,0x389b38ec,0x2e46bba8,0x3a8aba4f,
0xba6db6d7,0x37e3bb50,0xb8c43b3b,0xbaf6b67c,0x381d39ed,0xb93a3a8a,0x3addb95f,0x3a0f389b,0xb0b2bb88,0x3a4fb984,0xbbea3564,0xb8ecb9cb,
0xb3c63bfe,0xbb253848,0x3bc32a48,0x37323ac2,0x3b64361f,0xb4443b77,0x361fbb64,0x3bb635c2,0xbb64b61f,0x2cb5bbe2,0xb61f3b64,0xbbfab179,
0x3b64361f,0x2fd63bff,0x361fbb64,0x3bf1a648,0xbb64b61f,0xb505bbce,0xb61f3b64,0xbb993303,0xbbeab564,0x2648bb99,0xb0b23b88,0xbbffb505,
0x3bc3aa48,0x38483bb6,0xb3c6bbfe,0x3ac2b444,0xba6d36d7,0xbb50b93a,0x38c43b3b,0xb67c3a0f,0x381db9ed,0x3be22fd6,0xbaddb95f,0xb179bbf1,
0x3bf634a5,0x33033bb6,0xae46bba8,0x3bce3444,0xb913378b,0xbb77ba0f,0x3a2f3b0e,0xb5c2393a,0xae46bba8,0x3a8aafd6,0xbbf6b4a5,0xb89bbbf1,
0x3a2f3b0e,0x26483b25,0x3913b78b,0x3bff3732,0xbb88b3c6,0xb732bbce,0x35643bc3,0xbb25b303,0x2a48ba6d,0x3bb6367c,0xbbfeb8c4,0xb444bb50,
0x3b3b3add,0x2cb53a8a,0x36d7b81d,0x3bfa389b,0xb9ed30b2,0xbbf1b9cb,0x395f3bea,0xafd63984,0x3aa7323e,0x393a3be2,0xb872bbd9,0x3a0f3179,
0x38723bd9,0xb8ec2648,0x3aa7323e,0x3a4f3bff,0xbaa7b23e,0xbb25bbce,0x38723bd9,0xb7323303,0xb872bbd9,0x3444b67c,0xbaa7b23e,0xbbb6bb50,
0xb95fb0b2,0xba8abbf1,0x39ed3bea,0xb89bafd6,0xbb88bbc3,0x2648b732,0xb56433c6,0xbbffbb25,0xaa48b8c4,0x3ac237e3,0xbbfeba6d,0xb848baf6,
0x3b3b381d,0x3b503bfa,0xb6d7badd,0x367cacb5,0x378b2e46,0x3b773bfa,0xbb0ebbf6,0x35c22cb5,0x3ba83a2f,0x389b3a4f,0xb4a5b913,0x3a8a38ec,
0x3b0e3bf6,0x26483505,0x378b2e46,0x3bff3b99,0x34a53913,0xb848b444,0x3ba83a2f,0x3ac23bb6,0xb3c6aa48,0xbbf1bbff,0x3bc33bfe,0xafd6a648,
0xb8c4b6d7,0xbb99bbce,0x3a6d3b3b,0xb505b303,0xbaddb9ed,0xbaf6bb50,0x381d395f,0xb7e3b67c,0xbbeabb88,0xba0fba8a,0x30b23564,0xb93ab89b,
0x3c003c00,0xba4fb9cb,0,0xb8ecb984,0x3c003c00,0xbb25bac2,0,0xb732b848,0x3c003c00,0xbbb6bb77,0,0xb444b5c2,
0x3c003c00,0xbbfabbe2,0,0xacb5b179,0x33c62a48,0x367c393a,0x3bc33bfe,0xbb50ba0f,0x38c436d7,0xb1792fd6,0x3a6d3b3b,0xbbe2bbf1,
0x3add39ed,0xb984b732,0x381d395f,0xb9cbbb25,0x3bea3b88,0xbbcebaf6,0x30b23564,0xb303b7e3,0xbb0ebbf6,0x3be23a4f,0x378b2e46,0x317938ec,
0xb4a5b913,0x39843b99,0x3ba83a2f,0xb9cbb505,0x378b2e46,0xb3033444,0x3b0e3bf6,0xbbcebbb6,0x3ba83a2f,0xbb77b93a,0x34a53913,0xb5c2ba0f,
0xb95fb0b2,0x2cb5b89b,0xb9edbbea,0x3bfa3a8a,0xbb88bbc3,0x3bf13984,0x3564b3c6,0x2fd639cb,0xaa48b8c4,0x35053ac2,0x3bfe3a6d,0xbb99b848,
0x3b3b381d,0xbaf6b5c2,0x36d73add,0xb7e3bb77,0x38723bd9,0xbb99bac2,0xbaa7b23e,0x3505b848,0xbaa7b23e,0x37e3b5c2,0xb872bbd9,0x3af63b77,
0xb872bbd9,0x3a0f3be2,0x3aa7323e,0xb93a3179,0x3aa7323e,0xba4fa648,0x38723bd9,0xb8ecbbff,0x3b8833c6,0xb84837e3,0x35643bc3,0xbac2baf6,
0xaa483a6d,0xb67cbbfa,0xbbfeb8c4,0x3b502cb5,0xbb3bbadd,0x3be238ec,0x36d7b81d,0xb1793a4f,0x39edb0b2,0xb9843505,0x395f3bea,0xb9cbbb99,
0xae46bba8,0x39843b25,0x3bf634a5,0xb9cb3732,0x3a2f3b0e,0xbbceb7e3,0xb913378b,0x3303baf6,0xbbf6b4a5,0x3b77acb5,0xae46bba8,0x35c23bfa,
0x3913b78b,0xb89b38ec,0x3a2f3b0e,0xba8aba4f,0xbbeab564,0x3af6b67c,0x30b2bb88,0x37e33b50,0x3bc3aa48,0xba0f389b,0x33c63bfe,0xb93aba8a,
0xba6d36d7,0x38ecb9cb,0xb8c4bb3b,0x3a4f3984,0x381db9ed,0xb7323ac2,0x3add395f,0xbb25b848,0xb61f3b64,0xb444bb77,0xbb64b61f,0x3bb6b5c2,
0x361fbb64,0x2cb53be2,0x3b64361f,0xbbfa3179,0xb61f3b64,0x2fd6bbff,0xbb64b61f,0x3bf12648,0x361fbb64,0xb5053bce,0x3b64361f,0xbb99b303,
0x3a6d36d7,0xbbff3505,0xb8c43b3b,0xa648bb99,0xb81db9ed,0x3ac23444,0x3addb95f,0xb8483bb6,0x30b23b88,0xb67cba0f,0xbbea3564,0x3b50b93a,
0x33c6bbfe,0xb1793bf1,0x3bc32a48,0xbbe22fd6,0x3a2fbb0e,0xb3033bb6,0x3913378b,0xbbce3444,0xbbf634a5,0x3b77ba0f,0x2e46bba8,0x35c2393a,
0x3913378b,0xba8aafd6,0xba2f3b0e,0x389bbbf1,0x2e46bba8,0xa6483b25,0x3bf6b4a5,0xbbff3732,0xb6d7b81d,0x3b25b303,0x3b3bbadd,0xb7323bce,
0xb95f3bea,0x3444bb50,0xb9edb0b2,0x3bb6b67c,0x3b88b3c6,0xbbfa389b,0xb5643bc3,0x2cb5ba8a,0xaa48ba6d,0x2fd63984,0x3bfeb8c4,0xbbf139cb,
0xbbd93aa7,0x393abbe2,0xb23eb872,0x3a0fb179,0x323e3872,0xb8eca648,0xbbd93aa7,0x3a4fbbff,0x3bd9baa7,0xbb253bce,0x323e3872,0xb732b303,
0xb23eb872,0x3444367c,0x3bd9baa7,0xbbb63b50,0xaa4838c4,0xb89b2fd6,0xbbfe3a6d,0x3a8abbf1,0x3b3bb81d,0xbbff3b25,0xb6d73add,0xa648b732,
0x39edbbea,0xb8483af6,0x395fb0b2,0xbac237e3,0xb564b3c6,0x367c2cb5,0x3b88bbc3,0xbb503bfa,0x3ba8ba2f,0xbb773bfa,0xb4a53913,0xb5c22cb5,
0x3b0ebbf6,0xb89b3a4f,0x378bae46,0xba8a38ec,0x34a5b913,0xa6483505,0x3ba8ba2f,0xbbff3b99,0xb78b2e46,0x3848b444,0x3b0ebbf6,0xbac23bb6,
0x381db95f,0x2fd6a648,0x3addb9ed,0xbbf13bff,0x30b2b564,0x3505b303,0x3beabb88,0xbb993bce,0xb3c62a48,0x37e3b67c,0x3bc3bbfe,0xbaf63b50,
0xb8c436d7,0x393ab89b,0x3a6dbb3b,0xba0f3a8a,0xb9a839a8,0x3bf1bbff,0x39a8b9a8,0xafd62648,0xb9a839a8,0x3b99bbce,0x39a8b9a8,0xb5053303,
0xb9a839a8,0x3af6bb50,0x39a8b9a8,0xb7e3367c,0xb9a839a8,0x3a0fba8a,0x39a8b9a8,0xb93a389b,0xbadd39ed,0x35c2acb5,0xb81d395f,0x3b77bbfa,
0xbbea3b88,0x3a8ab8ec,0xb0b23564,0x389bba4f,0xbbc33bfe,0x3bffbb99,0x33c6aa48,0x2648b505,0xba6d3b3b,0x3ac2bbb6,0x38c4b6d7,0xb8483444,
0x34a5b913,0xba8a3bf1,0xbba83a2f,0x389bafd6,0xb78b2e46,0x26483732,0xbb0e3bf6,0x3bffbb25,0xbba83a2f,0x3ac2b7e3,0xb4a53913,0x3848baf6,
0xbb0e3bf6,0x3b50bbfa,0x378bae46,0xb67cacb5,0x3bfeba6d,0xba0f3179,0x2a48b8c4,0xb93a3be2,0x36d7badd,0xba4f3bff,0xbb3b381d,0x38ec2648,
0xb95f30b2,0x37323303,0xb9ed3bea,0x3b25bbce,0xbb883bc3,0x3bb6bb50,0x356433c6,0xb444b67c,0x323e3872,0x3732bbce,0x3bd9baa7,0xbb253303,
0x3bd9baa7,0xbbb6367c,0xb23eb872,0xb4443b50,0xb23eb872,0xacb53a8a,0xbbd93aa7,0x3bfab89b,0xbbd93aa7,0x3bf1b9cb,0x323e3872,0xafd6b984,
0xbb3b3add,0x3bceb444,0x36d7381d,0x3303bbb6,0x39ed30b2,0xb5c2b93a,0x395fbbea,0xbb773a0f,0x3564bbc3,0xb89b3bf1,0xbb8833c6,0x3a8a2fd6,
0xbbfe38c4,0x3bffb732,0x2a483a6d,0x2648bb25,0xb913b78b,0x26483b99,0xba2f3b0e,0x3bffb505,0xae463ba8,0x3848bbb6,0x3bf6b4a5,0xbac2b444,
0x3a2fbb0e,0xbb50393a,0xb913b78b,0x367c3a0f,0xbbf634a5,0x3be2afd6,0xae463ba8,0x3179bbf1,0x38c4bb3b,0xbbb635c2,0xba6db6d7,0x34443b77,
0xbadd395f,0x3bfab179,0x381d39ed,0xacb5bbe2,0x3beab564,0xbbf1a648,0xb0b2bb88,0xafd63bff,0xbbc3aa48,0x3b993303,0xb3c63bfe,0x3505bbce,
0x3b64361f,0xb7e3bb50,0x361fbb64,0xbaf6367c,0xbb64b61f,0x393a3a8a,0xb61f3b64,0x3a0fb89b,0x3b64361f,0xba4fb984,0x361fbb64,0xb8ec39cb,
0xbb64b61f,0x3b253848,0xb61f3b64,0x3732bac2,0xb0b23b88,0x39cbb732,0x3bea3564,0xb984bb25,0xb3c6bbfe,0xb3033af6,0xbbc32a48,0x3bce37e3,
0x38c43b3b,0xb5c2bbfa,0x3a6db6d7,0xbb772cb5,0xbaddb95f,0x3a8a3a4f,0xb81d39ed,0x389bb8ec,0xbbf6b4a5,0x3ac23af6,0x2e463ba8,0x3848b7e3,
0x3913b78b,0xbb50acb5,0xba2fbb0e,0x367c3bfa,0x2e463ba8,0x3179ba4f,0x3bf634a5,0xbbe2b8ec,0xba2fbb0e,0x39cb3b99,0xb913378b,0x3984b505,
0xb564bbc3,0xb5053848,0xbb88b3c6,0x3b993ac2,0x3bfe38c4,0xbaf6bb77,0x2a48ba6d,0xb7e335c2,0xb6d7381d,0x393ab179,0x3b3b3add,0xba0fbbe2,
0xb95fbbea,0x38ec3bff,0xb9ed30b2,0x3a4f2648,0x3aa7323e,0xbbfaba8a,0xb872bbd9,0xacb5389b,0x38723bd9,0xafd6b9cb,0x3aa7323e,0xbbf1b984,
0xbaa7b23e,0x3b993848,0x38723bd9,0xb505bac2,0xb872bbd9,0x37e33b77,0xbaa7b23e,0x3af635c2,0x39ed3bea,0xb179b8ec,0x395f30b2,0xbbe2ba4f,
0xb56433c6,0x39cb3505,0x3b883bc3,0xb984bb99,0xbbfeba6d,0x3bce3bb6,0x2a4838c4,0x3303b444,0xb6d7badd,0x35c23a0f,0xbb3bb81d,0x3b77393a,
0xb78bae46,0x3b503a0f,0x3b0e3bf6,0xb67cb93a,0xbba8ba2f,0x3be23bf1,0x34a53913,0x3179afd6,0xbb0ebbf6,0x39cb3b25,0xb78bae46,0x39843732,
0xb4a5b913,0x330337e3,0xbba8ba2f,0x3bce3af6,0xbbc3bbfe,0x38ec3984,0xb3c6aa48,0x3a4f39cb,0xba6dbb3b,0x37323848,0xb8c4b6d7,0x3b253ac2,
0xb81db95f,0x344435c2,0xbaddb9ed,0x3bb63b77,0xb0b2b564,0x2cb53179,0xbbeabb88,0x3bfa3be2,0x3c003c00,0x3a4f39cb,0,0x38ec3984,
0x3c003c00,0x3b253ac2,0,0x37323848,0x3c003c00,0x3bb63b77,0,0x344435c2,0x3c003c00,0x3bfa3be2,0,0x2cb53179,
0x33c62a48,0xb67cb93a,0x3bc33bfe,0x3b503a0f,0x38c436d7,0x3179afd6,0x3a6d3b3b,0x3be23bf1,0x3add39ed,0x39843732,0x381d395f,0x39cb3b25,
0x3bea3b88,0x3bce3af6,0x30b23564,0x330337e3,0xbb0ebbf6,0xbbe2ba4f,0x378b2e46,0xb179b8ec,0xb4a5b913,0xb984bb99,0x3ba83a2f,0x39cb3505,
0x378b2e46,0x3303b444,0x3b0e3bf6,0x3bce3bb6,0x3ba83a2f,0x3b77393a,0x34a53913,0x35c23a0f,0xb95fb0b2,0xacb5389b,0xb9edbbea,0xbbfaba8a,
0xbb88bbc3,0xbbf1b984,0x3564b3c6,0xafd6b9cb,0xaa48b8c4,0xb505bac2,0x3bfe3a6d,0x3b993848,0x3b3b381d,0x3af635c2,0x36d73add,0x37e33b77,
0x38723bd9,0x3b993ac2,0xbaa7b23e,0xb5053848,0xbaa7b23e,0xb7e335c2,0xb872bbd9,0xbaf6bb77,0xb872bbd9,0xba0fbbe2,0x3aa7323e,0x393ab179,
0x3aa7323e,0x3a4f2648,0x38723bd9,0x38ec3bff,0x3b8833c6,0x3848b7e3,0x35643bc3,0x3ac23af6,0xaa483a6d,0x367c3bfa,0xbbfeb8c4,0xbb50acb5,
0xbb3bbadd,0xbbe2b8ec,0x36d7b81d,0x3179ba4f,0x39edb0b2,0x3984b505,0x395f3bea,0x39cb3b99,0xae46bba8,0xb984bb25,0x3bf634a5,0x39cbb732,
0x3a2f3b0e,0x3bce37e3,0xb913378b,0xb3033af6,0xbbf6b4a5,0xbb772cb5,0xae46bba8,0xb5c2bbfa,0x3913b78b,0x389bb8ec,0x3a2f3b0e,0x3a8a3a4f,
0xbbeab564,0xbaf6367c,0x30b2bb88,0xb7e3bb50,0x3bc3aa48,0x3a0fb89b,0x33c63bfe,0x393a3a8a,0xba6d36d7,0xb8ec39cb,0xb8c4bb3b,0xba4fb984,
0x381db9ed,0x3732bac2,0x3add395f,0x3b253848,0xb61f3b64,0x34443b77,0xbb64b61f,0xbbb635c2,0x361fbb64,0xacb5bbe2,0x3b64361f,0x3bfab179,
0xb61f3b64,0xafd63bff,0xbb64b61f,0xbbf1a648,0x361fbb64,0x3505bbce,0x3b64361f,0x3b993303,0x3a6d36d7,0x3bffb505,0xb8c43b3b,0x26483b99,
0xb81db9ed,0xbac2b444,0x3addb95f,0x3848bbb6,0x30b23b88,0x367c3a0f,0xbbea3564,0xbb50393a,0x33c6bbfe,0x3179bbf1,0x3bc32a48,0x3be2afd6,
0x3a2fbb0e,0x3303bbb6,0x3913378b,0x3bceb444,0xbbf634a5,0xbb773a0f,0x2e46bba8,0xb5c2b93a,0x3913378b,0x3a8a2fd6,0xba2f3b0e,0xb89b3bf1,
0x2e46bba8,0x2648bb25,0x3bf6b4a5,0x3bffb732,0xb6d7b81d,0xbb253303,0x3b3bbadd,0x3732bbce,0xb95f3bea,0xb4443b50,0xb9edb0b2,0xbbb6367c,
0x3b88b3c6,0x3bfab89b,0xb5643bc3,0xacb53a8a,0xaa48ba6d,0xafd6b984,0x3bfeb8c4,0x3bf1b9cb,0xbbd93aa7,0xb93a3be2,0xb23eb872,0xba0f3179,
0x323e3872,0x38ec2648,0xbbd93aa7,0xba4f3bff,0x3bd9baa7,0x3b25bbce,0x323e3872,0x37323303,0xb23eb872,0xb444b67c,0x3bd9baa7,0x3bb6bb50,
0xaa4838c4,0x389bafd6,0xbbfe3a6d,0xba8a3bf1,0x3b3bb81d,0x3bffbb25,0xb6d73add,0x26483732,0x39edbbea,0x3848baf6,0x395fb0b2,0x3ac2b7e3,
0xb564b3c6,0xb67cacb5,0x3b88bbc3,0x3b50bbfa,0x3ba8ba2f,0x3b77bbfa,0xb4a53913,0x35c2acb5,0x3b0ebbf6,0x389bba4f,0x378bae46,0x3a8ab8ec,
0x34a5b913,0x2648b505,0x3ba8ba2f,0x3bffbb99,0xb78b2e46,0xb8483444,0x3b0ebbf6,0x3ac2bbb6,0x381db95f,0xafd62648,0x3addb9ed,0x3bf1bbff,
0x30b2b564,0xb5053303,0x3beabb88,0x3b99bbce,0xb3c62a48,0xb7e3367c,0x3bc3bbfe,0x3af6bb50,0xb8c436d7,0xb93a389b,0x3a6dbb3b,0x3a0fba8a,
0xb9a839a8,0xbbf13bff,0x39a8b9a8,0x2fd6a648,0xb9a839a8,0xbb993bce,0x39a8b9a8,0x3505b303,0xb9a839a8,0xbaf63b50,0x39a8b9a8,0x37e3b67c,
0xb9a839a8,0xba0f3a8a,0x39a8b9a8,0x393ab89b,0xbadd39ed,0xb5c22cb5,0xb81d395f,0xbb773bfa,0xbbea3b88,0xba8a38ec,0xb0b23564,0xb89b3a4f,
0xbbc33bfe,0xbbff3b99,0x33c6aa48,0xa6483505,0xba6d3b3b,0xbac23bb6,0x38c4b6d7,0x3848b444,0x34a5b913,0x3a8abbf1,0xbba83a2f,0xb89b2fd6,
0xb78b2e46,0xa648b732,0xbb0e3bf6,0xbbff3b25,0xbba83a2f,0xbac237e3,0xb4a53913,0xb8483af6,0xbb0e3bf6,0xbb503bfa,0x378bae46,0x367c2cb5,
0x3bfeba6d,0x3a0fb179,0x2a48b8c4,0x393abbe2,0x36d7badd,0x3a4fbbff,0xbb3b381d,0xb8eca648,0xb95f30b2,0xb732b303,0xb9ed3bea,0xbb253bce,
0xbb883bc3,0xbbb63b50,0x356433c6,0x3444367c,0x323e3872,0xb7323bce,0x3bd9baa7,0x3b25b303,0x3bd9baa7,0x3bb6b67c,0xb23eb872,0x3444bb50,
0xb23eb872,0x2cb5ba8a,0xbbd93aa7,0xbbfa389b,0xbbd93aa7,0xbbf139cb,0x323e3872,0x2fd63984,0xbb3b3add,0xbbce3444,0x36d7381d,0xb3033bb6,
0x39ed30b2,0x35c2393a,0x395fbbea,0x3b77ba0f,0x3564bbc3,0x389bbbf1,0xbb8833c6,0xba8aafd6,0xbbfe38c4,0xbbff3732,0x2a483a6d,0xa6483b25,
0xb913b78b,0xa648bb99,0xba2f3b0e,0xbbff3505,0xae463ba8,0xb8483bb6,0x3bf6b4a5,0x3ac23444,0x3a2fbb0e,0x3b50b93a,0xb913b78b,0xb67cba0f,
0xbbf634a5,0xbbe22fd6,0xae463ba8,0xb1793bf1,0x38c4bb3b,0x3bb6b5c2,0xba6db6d7,0xb444bb77,0xbadd395f,0xbbfa3179,0x381d39ed,0x2cb53be2,
0x3beab564,0x3bf12648,0xb0b2bb88,0x2fd6bbff,0xbbc3aa48,0xbb99b303,0xb3c63bfe,0xb5053bce,0x3b64361f,0x37e33b50,0x361fbb64,0x3af6b67c,
0xbb64b61f,0xb93aba8a,0xb61f3b64,0xba0f389b,0x3b64361f,0x3a4f3984,0x361fbb64,0x38ecb9cb,0xbb64b61f,0xbb25b848,0xb61f3b64,0xb7323ac2,
0xb0b23b88,0xb9cb3732,0x3bea3564,0x39843b25,0xb3c6bbfe,0x3303baf6,0xbbc32a48,0xbbceb7e3,0x38c43b3b,0x35c23bfa,0x3a6db6d7,0x3b77acb5,
0xbaddb95f,0xba8aba4f,0xb81d39ed,0xb89b38ec,0xbbf6b4a5,0xbac2baf6,0x2e463ba8,0xb84837e3,0x3913b78b,0x3b502cb5,0xba2fbb0e,0xb67cbbfa,
0x2e463ba8,0xb1793a4f,0x3bf634a5,0x3be238ec,0xba2fbb0e,0xb9cbbb99,0xb913378b,0xb9843505,0xb564bbc3,0x3505b848,0xbb88b3c6,0xbb99bac2,
0x3bfe38c4,0x3af63b77,0x2a48ba6d,0x37e3b5c2,0xb6d7381d,0xb93a3179,0x3b3b3add,0x3a0f3be2,0xb95fbbea,0xb8ecbbff,0xb9ed30b2,0xba4fa648,
0x3aa7323e,0x3bfa3a8a,0xb872bbd9,0x2cb5b89b,0x38723bd9,0x2fd639cb,0x3aa7323e,0x3bf13984,0xbaa7b23e,0xbb99b848,0x38723bd9,0x35053ac2,
0xb872bbd9,0xb7e3bb77,0xbaa7b23e,0xbaf6b5c2,0x39ed3bea,0x317938ec,0x395f30b2,0x3be23a4f,0xb56433c6,0xb9cbb505,0x3b883bc3,0x39843b99,
0xbbfeba6d,0xbbcebbb6,0x2a4838c4,0xb3033444,0xb6d7badd,0xb5c2ba0f,0xbb3bb81d,0xbb77b93a,0xb78bae46,0xbb50ba0f,0x3b0e3bf6,0x367c393a,
0xbba8ba2f,0xbbe2bbf1,0x34a53913,0xb1792fd6,0xbb0ebbf6,0xb9cbbb25,0xb78bae46,0xb984b732,0xb4a5b913,0xb303b7e3,0xbba8ba2f,0xbbcebaf6,
0xbbc3bbfe,0xb8ecb984,0xb3c6aa48,0xba4fb9cb,0xba6dbb3b,0xb732b848,0xb8c4b6d7,0xbb25bac2,0xb81db95f,0xb444b5c2,0xbaddb9ed,0xbbb6bb77,
0xb0b2b564,0xacb5b179,0xbbeabb88,0xbbfabbe2,0x3c003c00,0x96480000,0x3c003c00,0xa311a248,0x3c003c00,0x9cb69a48,0x3c003c00,0xa452a3db,
0x3c003c00,0x9fdb9e48,0x3c003c00,0xa51ba4b6,0x3c003c00,0xa17fa0b6,0x3bff3c00,0xa5e4a57f,0x3c003c00,0x9fdb0000,0x3bfb3bfc,0xac6aabd9,
0x3bff3c00,0xa5e4a3db,0x3bf93bfa,0xad65ace7,0x3bfe3bff,0xa8e8a7da,0x3bf63bf7,0xae5fade2,0x3bfd3bfe,0xaadea9e3,0x3bf23bf4,0xaf59aedc,
0x3c003c00,0xa3110000,0x3bf03bf4,0xafefaf0e,0x3bfe3bff,0xa94da711,0x3be83bed,0xb0d7b067,0x3bfb3bfd,0xac6aab11,0x3bdf3be4,0xb1b6b147,
0x3bf63bf9,0xae2dad4c,0x3bd43bda,0xb294b226,0x3c003c00,0xa51b0000,0x3bdf3be6,0xb1b6b115,0x3bfc3bfe,0xaba7a91b,0x3bcf3bd7,0xb2f7b257,
0x3bf63bf9,0xae5fad1a,0x3bbc3bc6,0xb41ab396,0x3bec3bf1,0xb074afa4,0x3ba53bb1,0xb4b7b469,0x3bff3c00,0xa6ad0000,0x3bc83bd4,0xb371b2a1,
0x3bfa3bfd,0xad00aaac,0x3bac3bbb,0xb487b420,0x3bef3bf5,0xb029aeaa,0x3b8b3b9d,0xb552b4ed,0x3bde3be7,0xb1cfb0fd,0x3b653b79,0xb61ab5b6,
0x3bff3c00,0xa81f0000,0x3bab3bbc,0xb493b414,0x3bf63bfc,0xae2dac1f,0x3b813b97,0xb58db511,0x3be53bef,0xb122b01d,0x3b4f3b69,0xb682b608,
0x3bcc3bda,0xb328b226,0x3b163b33,0xb76fb6f9,0x3bfe3c00,0xa8e80000,0x3b873ba0,0xb56ab4d5,0x3bf23bfa,0xaf59ace7,0x3b4c3b6b,0xb68db5fd,
0x3bda3be8,0xb219b0e4,0x3b073b2b,0xb7a6b71b,0x3bb73bca,0xb43eb34c,0x3ab63ae0,0xb85ab817,0x3bfe3c00,0xa9b10000,0x3b5e3b80,0xb63cb593,
0x3bee3bf8,0xb042adb0,0x3b103b39,0xb785b6e3,0x3bce3be0,0xb30fb1aa,0x3ab33ae3,0xb85fb812,0x3b9e3bb7,0xb4e7b438,0x3a493a7f,0xb8f3b8ab,
0x3bfd3c00,0xaa7a0000,0x3b2f3b5a,0xb70ab64e,0x3be83bf6,0xb0d7ae78,0x3acb3aff,0xb83ab7c2,0x3bbf3bd6,0xb402b26f,0x3a543a92,0xb8e5b891,
0x3b813ba2,0xb58db4c9,0x39cd3a13,0xb982b935,0x3bfd3c00,0xab430000,0x3afb3b30,0xb7d2b705,0x3be23bf3,0xb16caf40,0x3a7e3abf,0xb8adb84d,
0x3bae3bcb,0xb47bb334,0x39eb3a37,0xb962b909,0x3b603b8a,0xb631b558,0x3946399b,0xba04b9b5,0x3bfc3c00,0xac060000,0x3ac13b02,0xb84ab7b7,
0x3bdc3bf0,0xb201b004,0x3a293a78,0xb91bb8b5,0x3b9c3bc0,0xb4f3b3f7,0x397939d4,0xb9d6b97b,0x3b3d3b70,0xb6d2b5e5,0x38b23918,0xba7aba2b,
0x3bfb3c00,0xac6a0000,0x3a813ad0,0xb8a8b832,0x3bd43bed,0xb294b067,0x39cd3a2b,0xb982b918,0x3b873bb2,0xb56ab45d,0x38fd3969,0xba41b9e5,
0x3b163b53,0xb76fb670,0x3815388c,0xbae1ba95,0x3bfa3c00,0xacce0000,0x3a3d3a99,0xb902b887,0x3bcc3be9,0xb328b0cb,0x396b39d8,0xb9e3b976,
0x3b713ba4,0xb5dfb4bd,0x387a38f6,0xbaa2ba47,0x3aeb3b33,0xb805b6f9,0x36dd37ee,0xbb3abaf3,0x3bf93c00,0xad330000,0x39f43a5e,0xb958b8d8,
0x3bc33be5,0xb3bab12e,0x39023980,0xba3db9d0,0x3b593b95,0xb654b51d,0x37dd387c,0xbaf7baa0,0x3abd3b11,0xb850b780,0x358136b5,0xbb83bb43,
0x3bf83c00,0xad970000,0x39a63a1f,0xb9aab927,0x3bba3be1,0xb426b191,0x38943922,0xba90ba23,0x3b3f3b84,0xb6c6b57c,0x36bb37f9,0xbb42baf0,
0x3a8c3aed,0xb899b802,0x341a3570,0xbbbcbb86,0x3bf73c00,0xadfb0000,0x395439dc,0xb9f8b972,0x3bb03bdc,0xb46fb1f4,0x382038bf,0xbadbba71,
0x3b243b72,0xb737b5da,0x358d36ee,0xbb81bb36,0x3a583ac6,0xb8e0b842,0x31533420,0xbbe3bbbb,0x3bf63c00,0xae5f0000,0x38fd3996,0xba41b9ba,
0x3ba53bd7,0xb4b7b257,0x374e3858,0xbb1ebab8,0x3b073b5f,0xb7a6b637,0x345735da,0xbbb3bb72,0x3a213a9c,0xb924b881,0x2cce3191,0xbbfabbe1,
0x3bf53c00,0xaec30000,0x38a3394d,0xba85b9fe,0x3b9a3bd2,0xb4ffb2b9,0x365437d8,0xbb59baf9,0x3ae83b4b,0xb80ab693,0x323234bd,0xbbd9bba4,
0x39e73a71,0xb966b8bf,0xa4522db0,0xbc00bbf8,0x3bf33c00,0xaf270000,0x38453900,0xbac4ba3f,0x3b8e3bcd,0xb546b31b,0x355236f9,0xbb8bbb33,
0x3ac73b36,0xb840b6ee,0x2f593334,0xbbf2bbcb,0x39aa3a43,0xb9a6b8fb,0xaef51a48,0xbbf4bc00,0x3bf23c00,0xaf8b0000,0x37c838b0,0xbafeba7c,
0x3b813bc7,0xb58db37d,0x344b3614,0xbbb5bb67,0x3aa53b20,0xb874b748,0x288430e4,0xbbffbbe8,0x396b3a13,0xb9e3b935,0xb263ad4c,0xbbd7bbf9,
0x3bf03c00,0xafef0000,0x36ff385d,0xbb32bab5,0x3b733bc1,0xb5d4b3df,0x327c3529,0xbbd6bb93,0x3a813b08,0xb8a8b7a1,0xa9b12d1a,0xbbfebbf9,
0x392939e1,0xba1db96d,0xb49fb160,0xbba9bbe3,0x3bef3c00,0xb0290000,0x36313807,0xbb60bae9,0x3b653bbb,0xb61ab420,0x305b3438,0xbbedbbb7,
0x3a5c3af0,0xb8dbb7f9,0xafef1e48,0xbbf0bc00,0x38e539ad,0xba54b9a4,0xb602b408,0xbb6abbbe,0x3bed3c00,0xb05b0000,0x355e375e,0xbb89bb1a,
0x3b573bb4,0xb65fb451,0x2c6a3288,0xbbfbbbd5,0x3a353ad6,0xb90cb828,0xb27cac51,0xbbd6bbfb,0x389e3976,0xba89b9d8,0xb759b558,0xbb1bbb8a,
0x3beb3c00,0xb08d0000,0x348736aa,0xbbacbb46,0x3b473bad,0xb6a4b481,0x16483099,0xbc00bbeb,0x3a0d3abc,0xb93cb852,0xb47bb080,0xbbaebbec,
0x3855393e,0xbababa0b,0xb850b69e,0xbabdbb49,0x3be93c00,0xb0be0000,0x335935f1,0xbbc9bb6e,0x3b373ba6,0xb6e8b4b1,0xac382d4c,0xbbfcbbf9,
0x39e33aa0,0xb96bb87c,0xb5b1b2d2,0xbb7abbd1,0x380a3905,0xbae8ba3b,0xb8eab7d8,0xba50baf9,0x3be73c00,0xb0f00000,0x319e3534,0xbbe0bb91,
0x3b273b9e,0xb72cb4e1,0xb042257f,0xbbeebc00,0x39b83a83,0xb999b8a6,0xb6ddb48d,0xbb3abbab,0x377a38c9,0xbb13ba69,0xb979b881,0xb9d6ba9c,
0x3be53c00,0xb1220000,0x2fbd3475,0xbbf1bbaf,0x3b163b97,0xb76fb511,0xb263a91b,0xbbd7bbfe,0x398b3a65,0xb9c5b8ce,0xb7feb5ab,0xbaeebb7b,
0x36dd388c,0xbb3aba95,0xb9fcb90e,0xb94fba33,0x3be33c00,0xb1530000,0x2c383365,0xbbfcbbc9,0x3b043b8f,0xb7b2b540,0xb43eae78,0xbbb7bbf6,
0x395d3a47,0xb9f0b8f6,0xb889b6c1,0xba97bb41,0x363c384d,0xbb5ebabf,0xba73b992,0xb8bcb9be,0x3be13c00,0xb1850000,0x217f31db,0xbc00bbdd,
0x3af13b86,0xb7f3b570,0xb546b12e,0xbb8ebbe5,0x392e3a27,0xba19b91d,0xb90cb7cd,0xba35bafc,0x3599380d,0xbb7fbae6,0xbadbba0b,0xb820b93e,
0x3bdf3c00,0xb1b60000,0xa9b1304e,0xbbfebbed,0x3ade3b7d,0xb81ab59f,0xb648b31b,0xbb5cbbcd,0x38fd3a07,0xba41b943,0xb986b867,0xb9c9baae,
0x34f33796,0xbb9cbb0b,0xbb35ba78,0xb6f4b8b5,0x3bdd3c00,0xb1e80000,0xae5f2d7e,0xbbf6bbf8,0x3acb3b74,0xb83ab5ce,0xb742b481,0xbb21bbad,
0x38cc39e5,0xba67b969,0xb9f8b8e2,0xb954ba56,0x344b3710,0xbbb5bb2e,0xbb7fbad9,0xb599b822,0x3bda3c00,0xb2190000,0xb0f028b6,0xbbe7bbff,
0x3ab63b6b,0xb85ab5fd,0xb81ab570,0xbadebb86,0x389939c3,0xba8cb98d,0xba60b956,0xb8d6b9f6,0x33403687,0xbbcbbb4e,0xbbb8bb2e,0xb432b710,
0x3bff3bff,0xa6ada648,0x3bfe3bff,0xa8e8a8b6,0x3bff3bff,0xa776a711,0x3bfe3bfe,0xa94da91b,0x3bff3bff,0xa81fa7da,0x3bfe3bfe,0xa9b1a97f,
0x3bff3bff,0xa884a852,0x3bfe3bfe,0xaa16a9e3,0x3bef3bf1,0xb029afd6,0x3bda3bdd,0xb219b1db,0x3bea3bed,0xb0a6b067,0x3bd43bd7,0xb294b257,
0x3be53be8,0xb122b0e4,0x3bce3bd1,0xb30fb2d2,0x3be03be3,0xb19eb160,0x3bc63bca,0xb389b34c,0x3bc83bce,0xb371b303,0x3b873b91,0xb56ab534,
0x3bba3bc1,0xb426b3df,0x3b733b7d,0xb5d4b59f,0x3bab3bb2,0xb493b45d,0x3b5e3b69,0xb63cb608,0x3b9a3ba2,0xb4ffb4c9,0x3b473b53,0xb6a4b670,
0x3b8b3b99,0xb552b505,0x3b073b1a,0xb7a6b75e,0x3b6f3b7d,0xb5ebb59f,0x3ade3af3,0xb81ab7ee,0x3b4f3b5f,0xb682b637,0x3ab33ac9,0xb85fb83d,
0x3b2c3b3e,0xb715b6cc,0x3a853a9c,0xb8a3b881,0x3b3a3b50,0xb6ddb67c,0x3a5c3a7c,0xb8dbb8b0,0x3b0a3b22,0xb79bb73d,0x3a193a3b,0xb92eb905,
0x3ad53af0,0xb82ab7f9,0x39d239f6,0xb97db956,0x3a9b3ab8,0xb884b858,0x398639ad,0xb9c9b9a4,0x3ad53af6,0xb82ab7e3,0x398b39ba,0xb9c5b996,
0x3a8c3ab1,0xb899b862,0x3929395b,0xba1db9f2,0x3a3d3a65,0xb902b8ce,0x38c138f6,0xba6fba47,0x39e73a13,0xb966b935,0x3855388c,0xbababa95,
0x3a5c3a8a,0xb8dbb89b,0x389938d8,0xba8cba5e,0x39f83a2b,0xb954b918,0x38153858,0xbae1bab8,0x398b39c3,0xb9c5b98d,0x371537a1,0xbb2cbb08,
0x39163951,0xba2db9fa,0x35f73687,0xbb6cbb4e,0x39d23a0f,0xb97db93a,0x371537b7,0xbb2cbb02,0x394f3992,0xb9fcb9be,0x35c83670,0xbb76bb53,
0x38c13909,0xba6fba37,0x346f351d,0xbbb0bb95,0x382a3877,0xbad5baa3,0x3219337d,0xbbdabbc7,0x39373984,0xba11b9cb,0x34cf3593,0xbba1bb80,
0x389438e7,0xba90ba52,0x327c3408,0xbbd6bbbe,0x37c8383d,0xbafebac9,0x2e9130e4,0xbbf5bbe8,0x36543710,0xbb59bb2e,0x16482aac,0xbc00bbfd,
0x388e38ec,0xba93ba4f,0x30d732a1,0xbbe8bbd4,0x3790382d,0xbb0dbad3,0x28e82e14,0xbbfebbf7,0x35eb36c1,0xbb6fbb41,0xaccea4b6,0xbbfabc00,
0x34323511,0xbbb8bb97,0xb201b036,0xbbdcbbee,0x37b23848,0xbb04bac2,0x96482bd9,0xbc00bbfc,0x35df36cc,0xbb71bb3e,0xb010ac1f,0xbbefbbfc,
0x33eb34ed,0xbbc0bb9d,0xb402b20d,0xbbbfbbdb,0x2fef31f4,0xbbf0bbdc,0xb5ebb4f9,0xbb6fbb9b,0x36313732,0xbb60bb25,0xb0f0ad7e,0xbbe7bbf8,
0x341a3529,0xbbbcbb93,0xb49fb31b,0xbba9bbcd,0x2fbd320d,0xbbf1bbdb,0xb6afb5ab,0xbb45bb7b,0xa4522aac,0xbc00bbfd,0xb850b7ac,0xbabdbb05,
0x349f35c2,0xbba9bb77,0xb4dbb365,0xbb9fbbc9,0x308d32ea,0xbbebbbd0,0xb715b5fd,0xbb2cbb6b,0x9fdb2c51,0xbc00bbfb,0xb894b812,0xba90bae3,
0xb109ad4c,0xbbe6bbf9,0xb982b90e,0xb9cdba33,0x32013444,0xbbdcbbb6,0xb721b5f1,0xbb2abb6e,0x26ad2edc,0xbbffbbf4,0xb8adb822,0xba7ebad9,
0xb05bab11,0xbbedbbfd,0xb9aab930,0xb9a6ba17,0xb4b7b2ea,0xbba5bbd0,0xba81ba1b,0xb8a8b92b,0x2d653179,0xbbf9bbe2,0xb89eb807,0xba89bae9,
0xadc99a48,0xbbf8bc00,0xb9afb92b,0xb9a1ba1b,0xb432b1aa,0xbbb8bbe0,0xba93ba27,0xb88eb91d,0xb6d2b587,0xbb3dbb82,0xbb45baf3,0xb6afb7ee,
0xa51b2cb5,0xbc00bbfa,0xb990b900,0xb9c0ba3f,0xb294af40,0xbbd4bbf3,0xba89ba13,0xb89eb935,0xb625b4bd,0xbb63bba4,0xbb47baf0,0xb6a4b7f9,
0xb865b780,0xbab0bb11,0xbbc5bb8f,0xb3a2b540,0xafefa648,0xbbf0bbff,0xba60b9dc,0xb8d6b972,0xb517b31b,0xbb96bbcd,0xbb35bad3,0xb6f4b82d,
0xb7feb693,0xbaeebb4b,0xbbc0bb84,0xb3ebb57c,0xb94ab8ab,0xba00ba7f,0xbbfdbbe9,0xaa7ab0cb,0xb340afd6,0xbbcbbbf1,0xbb0aba99,0xb79bb887,
0xb6d2b540,0xbb3dbb8f,0xbbaebb67,0xb47bb614,0xb8dbb828,0xba5cbad6,0xbbfbbbe0,0xac9cb1aa,0xba15b980,0xb933b9d0,0xbbecbbff,0x30742852,
0xb53ab303,0xbb90bbce,0xbb89bb30,0xb55eb705,0xb83ab6e3,0xbacbbb39,0xbbf2bbca,0xaf8bb34c,0xb9a1b8f6,0xb9afba47,0xbbf5bc00,0x2ec39e48,
0xbac1ba3b,0xb84ab905,0xbb92bbd0,0x352f32ea,0xb6c6b505,0xbb3fbb99,0xbbdcbba0,0xb201b4d5,0xb8fdb838,0xba41bacc,0xbbfebbfb,0x2a16ac83,
0xba50b9b1,0xb8eab99f,0xbbaebbe4,0x347b3147,0xbb4abad9,0xb699b822,0xbaf1bb5d,0x37f33642,0xb820b67c,0xbadbbb50,0xbbffbbe6,0xa884b115,
0xb9afb8f1,0xb9a1ba4b,0xbbd2bbf8,0x32c62db0,0xbae5ba56,0xb80fb8e2,0xbb2abb8c,0x3721354c,0xbbaebb58,0xb47bb659,0xba11baaa,0x3937386d,
0xb8d1b7e3,0xba64baf6,0xbbf2bc00,0x2f8ba248,0xba4db99b,0xb8eeb9b5,0xbb6fbbc1,0x35eb33df,0xbb5cbae3,0xb648b812,0xba6bbafc,0x38c737cd,
0xbbebbbb4,0xb08db451,0xb8f8b9be,0x3a453992,0xb974b89b,0xb9daba8a,0xbbb5bbed,0x344b304e,0xbad5ba33,0xb82ab90e,0xbad8bb58,0x38253659,
0xbbb3bb55,0xb457b665,0xb979ba37,0x39d63909,0xbc00bbed,0x9648b067,0xb764b8a0,0x3b183a87,0xba09b93a,0xb941ba0f,0xbb4abbaf,0x36993475,
0xbb45bab8,0xb6afb858,0xba11babf,0x3937384d,0xbbeabbab,0xb0a6b48d,0xb85ab943,0x3ab63a07,0xbbecbc00,0x30749a48,0xb493b6b5,0x3bab3b43,
0xba8cb9cb,0xb899b984,0xbab3bb46,0x385f36aa,0xbb9cbb28,0xb4f3b726,0xb91fb9fa,0x3a253951,0xbc00bbe4,0xa452b147,0xb631b828,0x3b603ad6,
0xbbb0bbee,0x346f3036,0xae5fb3df,0x3bf63bc1,0xbafeba4f,0xb7c8b8ec,0xb9f4bab5,0x3958385d,0xbbd8bb82,0xb24bb587,0xb80ab90e,0x3ae83a33,
0xbbf3bbfe,0x2f27a97f,0xb2f7b5da,0x3bcf3b72,0xbb4cbbb7,0x368d3438,0x2dc9ac1f,0x3bf83bfc,0xbb5cbac2,0xb648b848,0xb911b9fe,0x3a31394d,
0xbbf9bbc4,0xad33b3ae,0xb5b1b802,0x3b7a3aed,0xbbc5bbf9,0x33a22d1a,0xa94db26f,0x3bfe3bd6,0xbac4bb5d,0x38453642,0x346f2fa4,0x3bb03bf1,
0xbba5bb25,0xb4b7b732,0xb80fb927,0x3ae53a1f,0xbbffbbee,0x2884b036,0xb24bb5b6,0x3bd83b79,0xbb76bbd6,0x35c8326f,0x305ba7da,0x3bed3bff,
0xba19bae0,0x392e3817,0x374234c9,0x3b213ba2,0xbbd9bb77,0xb232b5c2,0xb5ebb832,0x3b6f3ad0,0xbbe8bc00,0x30d7a57f,0xa81fb288,0x3bff3bd5,
0xbb07bb95,0x37a6351d,0x34f33080,0x3b9c3bec,0xb94fba43,0x39fc38fb,0x38ea3780,0x3a503b11,0xbbf8bbb6,0xadc9b444,0xb328b64e,0x3bcc3b5a,
0xbbb7bbf8,0x343e2db0,0x3042a9e3,0x3bee3bfe,0xba7abb36,0x38b236ee,0x379034ed,0x3b0d3b9d,0xb86ab989,0x3aac39c7,0x3a0438fb,0x39463a43,
0xbc00bbe2,0x2311b179,0xac9cb414,0x3bfb3bbc,0xbb6abbd7,0x36023257,0x34b72f40,0x3ba53bf3,0xb9d2babc,0x397d3852,0x38f83775,0x3a453b14,
0xb6ddb8b5,0x3b3a3a78,0x3ae83a0b,0x380a393e,0xbbf2bbfa,0x2f8bacb5,0x2d33af0e,0x3bf93bf4,0xbb04bb9e,0x37b234e1,0x372c3451,0x3b273bb4,
0xb911ba27,0x3a31391d,0x3a0038e2,0x394a3a56,0xb4c3b796,0x3ba33b0b,0x3b8b3ae6,0x3552380d,0x4c004c00,0x26480000,0x4c004c00,0x33113248,
0x4c004c00,0x2cb62a48,0x4c004c00,0x345233db,0x4c004c00,0x2fdb2e48,0x4c004c00,0x351b34b6,0x4c004c00,0x317f30b6,0x4bff4c00,0x35e4357f,
0x4c004c00,0x2fdb0000,0x4bfb4bfc,0x3c6a3bd9,0x4bff4c00,0x35e433db,0x4bf94bfa,0x3d653ce7,0x4bfe4bff,0x38e837da,0x4bf64bf7,0x3e5f3de2,
0x4bfd4bfe,0x3ade39e3,0x4bf24bf4,0x3f593edc,0x4c004c00,0x33110000,0x4bf04bf4,0x3fef3f0e,0x4bfe4bff,0x394d3711,0x4be84bed,0x40d74067,
0x4bfb4bfd,0x3c6a3b11,0x4bdf4be4,0x41b64147,0x4bf64bf9,0x3e2d3d4c,0x4bd44bda,0x42944226,0x4c004c00,0x351b0000,0x4bdf4be6,0x41b64115,
0x4bfc4bfe,0x3ba7391b,0x4bcf4bd7,0x42f74257,0x4bf64bf9,0x3e5f3d1a,0x4bbc4bc6,0x441a4396,0x4bec4bf1,0x40743fa4,0x4ba54bb1,0x44b74469,
0x4bff4c00,0x36ad0000,0x4bc84bd4,0x437142a1,0x4bfa4bfd,0x3d003aac,0x4bac4bbb,0x44874420,0x4bef4bf5,0x40293eaa,0x4b8b4b9d,0x455244ed,
0x4bde4be7,0x41cf40fd,0x4b654b79,0x461a45b6,0x4bff4c00,0x381f0000,0x4bab4bbc,0x44934414,0x4bf64bfc,0x3e2d3c1f,0x4b814b97,0x458d4511,
0x4be54bef,0x4122401d,0x4b4f4b69,0x46824608,0x4bcc4bda,0x43284226,0x4b164b33,0x476f46f9,0x4bfe4c00,0x38e80000,0x4b874ba0,0x456a44d5,
0x4bf24bfa,0x3f593ce7,0x4b4c4b6b,0x468d45fd,0x4bda4be8,0x421940e4,0x4b074b2b,0x47a6471b,0x4bb74bca,0x443e434c,0x4ab64ae0,0x485a4817,
0x4bfe4c00,0x39b10000,0x4b5e4b80,0x463c4593,0x4bee4bf8,0x40423db0,0x4b104b39,0x478546e3,0x4bce4be0,0x430f41aa,0x4ab34ae3,0x485f4812,
0x4b9e4bb7,0x44e74438,0x4a494a7f,0x48f348ab,0x4bfd4c00,0x3a7a0000,0x4b2f4b5a,0x470a464e,0x4be84bf6,0x40d73e78,0x4acb4aff,0x483a47c2,
0x4bbf4bd6,0x4402426f,0x4a544a92,0x48e54891,0x4b814ba2,0x458d44c9,0x49cd4a13,0x49824935,0x4bfd4c00,0x3b430000,0x4afb4b30,0x47d24705,
0x4be24bf3,0x416c3f40,0x4a7e4abf,0x48ad484d,0x4bae4bcb,0x447b4334,0x49eb4a37,0x49624909,0x4b604b8a,0x46314558,0x4946499b,0x4a0449b5,
0x4bfc4c00,0x3c060000,0x4ac14b02,0x484a47b7,0x4bdc4bf0,0x42014004,0x4a294a78,0x491b48b5,0x4b9c4bc0,0x44f343f7,0x497949d4,0x49d6497b,
0x4b3d4b70,0x46d245e5,0x48b24918,0x4a7a4a2b,0x4bfb4c00,0x3c6a0000,0x4a814ad0,0x48a84832,0x4bd44bed,0x42944067,0x49cd4a2b,0x49824918,
0x4b874bb2,0x456a445d,0x48fd4969,0x4a4149e5,0x4b164b53,0x476f4670,0x4815488c,0x4ae14a95,0x4bfa4c00,0x3cce0000,0x4a3d4a99,0x49024887,
0x4bcc4be9,0x432840cb,0x496b49d8,0x49e34976,0x4b714ba4,0x45df44bd,0x487a48f6,0x4aa24a47,0x4aeb4b33,0x480546f9,0x46dd47ee,0x4b3a4af3,
0x4bf94c00,0x3d330000,0x49f44a5e,0x495848d8,0x4bc34be5,0x43ba412e,0x49024980,0x4a3d49d0,0x4b594b95,0x4654451d,0x47dd487c,0x4af74aa0,
0x4abd4b11,0x48504780,0x458146b5,0x4b834b43,0x4bf84c00,0x3d970000,0x49a64a1f,0x49aa4927,0x4bba4be1,0x44264191,0x48944922,0x4a904a23,
0x4b3f4b84,0x46c6457c,0x46bb47f9,0x4b424af0,0x4a8c4aed,0x48994802,0x441a4570,0x4bbc4b86,0x4bf74c00,0x3dfb0000,0x495449dc,0x49f84972,
0x4bb04bdc,0x446f41f4,0x482048bf,0x4adb4a71,0x4b244b72,0x473745da,0x458d46ee,0x4b814b36,0x4a584ac6,0x48e04842,0x41534420,0x4be34bbb,
0x4bf64c00,0x3e5f0000,0x48fd4996,0x4a4149ba,0x4ba54bd7,0x44b74257,0x474e4858,0x4b1e4ab8,0x4b074b5f,0x47a64637,0x445745da,0x4bb34b72,
0x4a214a9c,0x49244881,0x3cce4191,0x4bfa4be1,0x4bf54c00,0x3ec30000,0x48a3494d,0x4a8549fe,0x4b9a4bd2,0x44ff42b9,0x465447d8,0x4b594af9,
0x4ae84b4b,0x480a4693,0x423244bd,0x4bd94ba4,0x49e74a71,0x496648bf,0xb4523db0,0x4c004bf8,0x4bf34c00,0x3f270000,0x48454900,0x4ac44a3f,
0x4b8e4bcd,0x4546431b,0x455246f9,0x4b8b4b33,0x4ac74b36,0x484046ee,0x3f594334,0x4bf24bcb,0x49aa4a43,0x49a648fb,0xbef52a48,0x4bf44c00,
0x4bf24c00,0x3f8b0000,0x47c848b0,0x4afe4a7c,0x4b814bc7,0x458d437d,0x444b4614,0x4bb54b67,0x4aa54b20,0x48744748,0x388440e4,0x4bff4be8,
0x496b4a13,0x49e34935,0xc263bd4c,0x4bd74bf9,0x4bf04c00,0x3fef0000,0x46ff485d,0x4b324ab5,0x4b734bc1,0x45d443df,0x427c4529,0x4bd64b93,
0x4a814b08,0x48a847a1,0xb9b13d1a,0x4bfe4bf9,0x492949e1,0x4a1d496d,0xc49fc160,0x4ba94be3,0x4bef4c00,0x40290000,0x46314807,0x4b604ae9,
0x4b654bbb,0x461a4420,0x405b4438,0x4bed4bb7,0x4a5c4af0,0x48db47f9,0xbfef2e48,0x4bf04c00,0x48e549ad,0x4a5449a4,0xc602c408,0x4b6a4bbe,
0x4bed4c00,0x405b0000,0x455e475e,0x4b894b1a,0x4b574bb4,0x465f4451,0x3c6a4288,0x4bfb4bd5,0x4a354ad6,0x490c4828,0xc27cbc51,0x4bd64bfb,
0x489e4976,0x4a8949d8,0xc759c558,0x4b1b4b8a,0x4beb4c00,0x408d0000,0x448746aa,0x4bac4b46,0x4b474bad,0x46a44481,0x26484099,0x4c004beb,
0x4a0d4abc,0x493c4852,0xc47bc080,0x4bae4bec,0x4855493e,0x4aba4a0b,0xc850c69e,0x4abd4b49,0x4be94c00,0x40be0000,0x435945f1,0x4bc94b6e,
0x4b374ba6,0x46e844b1,0xbc383d4c,0x4bfc4bf9,0x49e34aa0,0x496b487c,0xc5b1c2d2,0x4b7a4bd1,0x480a4905,0x4ae84a3b,0xc8eac7d8,0x4a504af9,
0x4be74c00,0x40f00000,0x419e4534,0x4be04b91,0x4b274b9e,0x472c44e1,0xc042357f,0x4bee4c00,0x49b84a83,0x499948a6,0xc6ddc48d,0x4b3a4bab,
0x477a48c9,0x4b134a69,0xc979c881,0x49d64a9c,0x4be54c00,0x41220000,0x3fbd4475,0x4bf14baf,0x4b164b97,0x476f4511,0xc263b91b,0x4bd74bfe,
0x498b4a65,0x49c548ce,0xc7fec5ab,0x4aee4b7b,0x46dd488c,0x4b3a4a95,0xc9fcc90e,0x494f4a33,0x4be34c00,0x41530000,0x3c384365,0x4bfc4bc9,
0x4b044b8f,0x47b24540,0xc43ebe78,0x4bb74bf6,0x495d4a47,0x49f048f6,0xc889c6c1,0x4a974b41,0x463c484d,0x4b5e4abf,0xca73c992,0x48bc49be,
0x4be14c00,0x41850000,0x317f41db,0x4c004bdd,0x4af14b86,0x47f34570,0xc546c12e,0x4b8e4be5,0x492e4a27,0x4a19491d,0xc90cc7cd,0x4a354afc,
0x4599480d,0x4b7f4ae6,0xcadbca0b,0x4820493e,0x4bdf4c00,0x41b60000,0xb9b1404e,0x4bfe4bed,0x4ade4b7d,0x481a459f,0xc648c31b,0x4b5c4bcd,
0x48fd4a07,0x4a414943,0xc986c867,0x49c94aae,0x44f34796,0x4b9c4b0b,0xcb35ca78,0x46f448b5,0x4bdd4c00,0x41e80000,0xbe5f3d7e,0x4bf64bf8,
0x4acb4b74,0x483a45ce,0xc742c481,0x4b214bad,0x48cc49e5,0x4a674969,0xc9f8c8e2,0x49544a56,0x444b4710,0x4bb54b2e,0xcb7fcad9,0x45994822,
0x4bda4c00,0x42190000,0xc0f038b6,0x4be74bff,0x4ab64b6b,0x485a45fd,0xc81ac570,0x4ade4b86,0x489949c3,0x4a8c498d,0xca60c956,0x48d649f6,
0x43404687,0x4bcb4b4e,0xcbb8cb2e,0x44324710,0x4bd84c00,0x424b0000,0xc2adb248,0x4bd34c00,0x4aa24b62,0x487a462b,0xc88ec659,0x4a934b58,
0x4865499f,0x4ab049b1,0xcabdc9c3,0x4850498d,0x41e845fd,0x4bdd4b6b,0xcbe1cb74,0x418545ce,0x4bd64c00,0x427c0000,0xc432bbd9,0x4bb84bfc,
0x4a8c4b58,0x48994659,0xc8fdc73d,0x4a414b22,0x4830497b,0x4ad149d4,0xcb10ca27,0x4785491d,0x408d4570,0x4beb4b86,0xcbf9cbad,0x3d334481,
0x4bd34c00,0x42ad0000,0xc50bbf0e,0x4b984bf4,0x4a764b4e,0x48b74687,0xc966c80d,0x49e74ae6,0x47f34956,0x4af149f6,0xcb57ca83,0x465f48a6,
0x3e5f44e1,0x4bf64b9e,0xcc00cbd7,0xb17f4257,0x4bd04c00,0x42de0000,0xc5dfc115,0x4b714be6,0x4a604b43,0x48d646b5,0xc9c9c877,0x49864aa3,
0x47854930,0x4b104a17,0xcb92cad6,0x452f4828,0x3b434451,0x4bfd4bb4,0xcbf5cbf3,0xbe913f40,0x4bce4c00,0x430f0000,0xc6afc2a1,0x4b454bd4,
0x4a494b39,0x48f346e3,0xca25c8dd,0x491f4a5a,0x47154909,0x4b2c4a37,0xcbc0cb20,0x43eb4748,0x3311437d,0x4c004bc7,0xcbd9cbff,0xc2323711,
0x4bcb4c00,0x43400000,0xc77ac414,0x4b134bbc,0x4a314b2e,0x49114710,0xca7ac93e,0x48b24a0b,0x46a448e2,0x4b474a56,0xcbe2cb5f,0x416c4637,
0xb7764257,0x4bff4bd7,0xcbaccbfd,0xc487bb75,0x4bc84c00,0x43710000,0xc820c4d5,0x4adb4ba0,0x4a194b22,0x492e473d,0xcac7c99b,0x484049b5,
0x463148ba,0x4b604a74,0xcbf8cb95,0x3dc9451d,0xbc9c412e,0x4bfb4be5,0xcb6fcbeb,0xc5ebc099,0x4bc54c00,0x43a20000,0xc87fc593,0x4a9e4b80,
0x4a004b17,0x494a476a,0xcb0dc9f2,0x4790495b,0x45bc4891,0x4b784a92,0xcc00cbc0,0x317f43f7,0xbf594004,0x4bf24bf0,0xcb21cbca,0xc742c34c,
0x4bc24c00,0x43d30000,0xc8dbc64e,0x4a5c4b5a,0x49e74b0b,0x49664796,0xcb4aca43,0x469948fb,0x45464867,0x4b8e4aae,0xcbfbcbe0,0xbc6a41aa,
0xc1093db0,0x4be64bf8,0xcac4cb9b,0xc845c4f9,0x4bbf4c00,0x44020000,0xc933c705,0x4a154b30,0x49cd4aff,0x498247c2,0xcb7fca8e,0x45994896,
0x44cf483d,0x4ba14ac9,0xcbe9cbf5,0xc0be3eaa,0xc2633aac,0x4bd74bfd,0xca58cb5d,0xc8e0c642,0x4bbc4c00,0x441a0000,0xc986c7b7,0x49c94b02,
0x49b34af3,0x499d47ee,0xcbabcad3,0x4493482d,0x44574812,0x4bb34ae3,0xcbcbcbff,0xc34037da,0xc3ba33db,0x4bc34c00,0xc9dfcb11,0xc970c780,
0x4bb84c00,0x44320000,0xc9d6c832,0x49794ad0,0x49994ae6,0x49b8480d,0xcbcecb11,0x430f4780,0x43ba47cd,0x4bc34afc,0xcb9fcbfe,0xc4dbb97f,
0xc487b57f,0x4bac4c00,0xc958cab8,0xc9f4c858,0x4bb54c00,0x444b0000,0xca21c887,0x49244a99,0x497d4ad9,0x49d24822,0xcbe7cb49,0x40f0469e,
0x42c64775,0x4bd24b14,0xcb68cbf2,0xc60ebf72,0xc52fbb75,0x4b924bfd,0xc8c7ca52,0xca6bc8e7,0x4bb24c00,0x44630000,0xca67c8d8,0x48cc4a5e,
0x49624acc,0x49eb4838,0xcbf8cb79,0x3d9745b6,0x41cf471b,0x4bde4b2b,0xcb24cbdb,0xc737c20d,0xc5d4be14,0x4b734bf7,0xc82ac9e1,0xcad5c96d,
0x4bae4c00,0x447b0000,0xcaa9c927,0x486f4a1f,0x49464abf,0x4a04484d,0xcc00cba2,0x351b44c9,0x40d746c1,0x4be84b41,0xcad5cbb9,0xc82ac42c,
0xc676c036,0x4b524bee,0xc70ac964,0xcb2fc9e9,0x4bab4c00,0x44930000,0xcae5c972,0x480f49dc,0x49294ab1,0x4a1d4862,0xcbfecbc4,0xba1643ae,
0x3fbd4665,0x4bf14b55,0xca7acb8c,0xc8b2c54c,0xc715c160,0x4b2c4be3,0xc5b1c8dd,0xcb7aca5a,0x4ba74c00,0x44ab0000,0xcb1bc9ba,0x47594996,
0x490c4aa3,0x4a354877,0xcbf2cbdf,0xbf5941c3,0x3dc94608,0x4bf84b69,0xca15cb55,0xc933c665,0xc7b2c288,0x4b044bd5,0xc44bc84d,0xcbb5cabf,
0x4ba34c00,0x44c30000,0xcb4cc9fe,0x468d494d,0x48ee4a95,0x4a4d488c,0xcbdecbf1,0xc1cf3fa4,0x3ba745ab,0x4bfc4b7b,0xc9a6cb14,0xc9aac775,
0xc825c3ae,0x4ad84bc4,0xc1b6c76a,0xcbdfcb17,0x4b9f4c00,0x44db0000,0xcb78ca3f,0x45bc4900,0x48d14a87,0x4a6448a0,0xcbc0cbfd,0xc3eb3b75,
0x3776454c,0x4bff4b8c,0xc92ecac9,0xca19c83d,0xc86fc469,0x4aa94bb1,0xbd97c62b,0xcbf8cb62,0x4b9c4c00,0x44f30000,0xcb9eca7c,0x44e748b0,
0x48b24a78,0x4a7a48b5,0xcb9acc00,0xc4ffaa48,0xa64844ed,0x4c004b9d,0xc8adca74,0xca7ec8ba,0xc8b7c4f9,0x4a764b9b,0x2cb6c4e1,0xcc00cb9e,
0x4b984c00,0x450b0000,0xcbbdcab5,0x440e485d,0x48944a69,0x4a9048c9,0xcb6acbfc,0xc602bc1f,0xb81f448d,0x4bff4bab,0xc825ca17,0xcad8c930,
0xc8fdc587,0x4a414b82,0x3e2dc31b,0xcbf6cbcd,0x4b944c00,0x45230000,0xcbd7cae9,0x42634807,0x48744a5a,0x4aa548dd,0xcb32cbf0,0xc6ffc004,
0xbc06442c,0x4bfc4bb9,0xc72cc9b1,0xcb27c99f,0xc941c614,0x4a094b67,0x4201c067,0xcbdccbed,0x4b904c00,0x453a0000,0xcbeacb1a,0x40a6475e,
0x48554a4b,0x4aba48f1,0xcaf1cbdc,0xc7f3c1f4,0xbdfb4396,0x4bf74bc6,0xc602c943,0xcb6aca07,0xc982c69e,0x49cd4b49,0x446fbaac,0xcbb0cbfd,
0x4b8b4c00,0x45520000,0xcbf8cb46,0x3dc946aa,0x48354a3b,0x4ace4905,0xcaa9cbc1,0xc86fc3df,0xbfef42d2,0x4bf04bd1,0xc4cfc8ce,0xcba1ca65,
0xc9c0c726,0x49904b28,0x45d43852,0xcb73cbff,0x4b874c00,0x456a0000,0xcbffcb6e,0x388445f1,0x48154a2b,0x4ae14918,0xca58cb9e,0xc8e0c4e1,
0xc0f0420d,0x4be74bdb,0xc328c852,0xcbcccabc,0xc9fcc7ac,0x494f4b05,0x472c3fa4,0xcb27cbf1,0x4b834c00,0x45810000,0xcc00cb91,0xb51b4534,
0x47e84a1b,0x4af4492b,0xca00cb74,0xc94ac5ce,0xc1e84147,0x4bdd4be4,0xc0a6c7a1,0xcbeacb08,0xca35c817,0x490c4ae0,0x483a4288,0xcacbcbd5,
0x4b7f4c00,0x45990000,0xcbfacbaf,0xbcce4475,0x47a64a0b,0x4b07493e,0xc9a1cb43,0xc9afc6b5,0xc2de4080,0x4bd04bec,0xbc38c693,0xcbfccb4b,
0xca6bc858,0x48c74ab8,0x48d64499,0xca60cbaa,0x4b7a4c00,0x45b10000,0xcbefcbc9,0xc0294365,0x476449fa,0x4b184951,0xc93ccb0b,0xca0dc796,
0xc3d33f72,0x4bc24bf2,0x3311c57c,0xcc00cb84,0xca9ec896,0x487f4a8e,0x496645e5,0xc9e7cb70,0x4b764c00,0x45c80000,0xcbddcbdd,0xc1e841db,
0x472149e9,0x4b2a4964,0xc8d1cacc,0xca64c838,0xc4633de2,0x4bb24bf7,0x3dfbc45d,0xcbf7cbb2,0xcacec8d3,0x48354a62,0x49eb4726,0xc962cb28,
0x4b714c00,0x45df0000,0xcbc5cbed,0xc3a2404e,0x46dd49d8,0x4b3a4976,0xc85fca87,0xcab3c8a0,0xc4db3c51,0x4b9f4bfb,0x4185c26f,0xcbe1cbd6,
0xcafbc90e,0x47d24a33,0x4a64482d,0xc8d1cad3,0x4b6c4c00,0x45f70000,0xcba7cbf8,0xc4ab3d7e,0x469949c7,0x4b4a4989,0xc7d2ca3b,0xcafbc905,
0xc552397f,0x4b8b4bfe,0x4402c01d,0xcbbfcbef,0xcb24c948,0x47374a02,0x4ace48bf,0xc835ca71,0x4b684c00,0x460e0000,0xcb83cbff,0xc58138b6,
0x465449b5,0x4b59499b,0xc6ddc9e9,0xcb3ac964,0xc5c834b6,0x4b764c00,0x453abb11,0xcb90cbfd,0xcb4ac980,0x469949d0,0x4b2a4948,0xc721ca02,
0x2c002c00,0x2c002c00,0x2c002c00,0x2c002c00,0x2b642c00,0x261f29a8,0xa61f0000,0xab64a9a8,0x29a82c00,0xa9a80000,0xa9a8ac00,0x29a80000,
0x261f2c00,0xab64a9a8,0x2b640000,0xa61f29a8,0x2c00,0xac00,0x2c00,0xac00,0xa61f2c00,0x2b64a9a8,0xab640000,0x261f29a8,
0xa9a82c00,0x29a80000,0x29a8ac00,0xa9a80000,0xab642c00,0xa61f29a8,0x261f0000,0x2b64a9a8,0,0,0,0,
0x261f0000,0x2b6429a8,0x2b642c00,0x261f29a8,0x29a80000,0x29a82c00,0xa9a80000,0xa9a8ac00,0x2b640000,0xa61f29a8,0xa61fac00,0x2b6429a8,
0x2c000000,0xac000000,0x2c000000,0xac000000,0x2b640000,0xa61fa9a8,0xa61f2c00,0x2b64a9a8,0x29a80000,0x29a8ac00,0xa9a80000,0xa9a82c00,
0x261f0000,0x2b64a9a8,0x2b64ac00,0x261fa9a8,0xac002c00,0xac002c00,0xac002c00,0xac002c00,0xab642c00,0xa61f29a8,0x261f0000,0x2b64a9a8,
0xa9a82c00,0x29a80000,0x29a8ac00,0xa9a80000,0xa61f2c00,0x2b64a9a8,0xab640000,0x261f29a8,0x2c00,0xac00,0x2c00,0xac00,
0x261f2c00,0xab64a9a8,0x2b640000,0xa61f29a8,0x29a82c00,0xa9a80000,0xa9a8ac00,0x29a80000,0x2b642c00,0x261f29a8,0xa61f0000,0xab64a9a8,
0,0,0,0,0xa61f0000,0xab6429a8,0xab642c00,0xa61f29a8,0xa9a80000,0xa9a82c00,0x29a80000,0x29a8ac00,
0xab640000,0x261f29a8,0x261fac00,0xab6429a8,0xac000000,0x2c000000,0xac000000,0x2c000000,0xab640000,0x261fa9a8,0x261f2c00,0xab64a9a8,
0xa9a80000,0xa9a8ac00,0x29a80000,0x29a82c00,0xa61f0000,0xab64a9a8,0xab64ac00,0xa61fa9a8,0,0,0,0,
0xa61f0000,0xab64a9a8,0xab64ac00,0xa61fa9a8,0xa9a80000,0xa9a8ac00,0x29a80000,0x29a82c00,0xab640000,0x261fa9a8,0x261f2c00,0xab64a9a8,
0xac000000,0x2c000000,0xac000000,0x2c000000,0xab640000,0x261f29a8,0x261fac00,0xab6429a8,0xa9a80000,0xa9a82c00,0x29a80000,0x29a8ac00,
0xa61f0000,0xab6429a8,0xab642c00,0xa61f29a8,0x2c002c00,0x2c002c00,0x2c002c00,0x2c002c00,0x2b642c00,0x261f29a8,0xa61f0000,0xab64a9a8,
0x29a82c00,0xa9a80000,0xa9a8ac00,0x29a80000,0x261f2c00,0xab64a9a8,0x2b640000,0xa61f29a8,0x2c00,0xac00,0x2c00,0xac00,
0xa61f2c00,0x2b64a9a8,0xab640000,0x261f29a8,0xa9a82c00,0x29a80000,0x29a8ac00,0xa9a80000,0xab642c00,0xa61f29a8,0x261f0000,0x2b64a9a8,
0,0,0,0,0x261f0000,0x2b64a9a8,0x2b64ac00,0x261fa9a8,0x29a80000,0x29a8ac00,0xa9a80000,0xa9a82c00,
0x2b640000,0xa61fa9a8,0xa61f2c00,0x2b64a9a8,0x2c000000,0xac000000,0x2c000000,0xac000000,0x2b640000,0xa61f29a8,0xa61fac00,0x2b6429a8,
0x29a80000,0x29a82c00,0xa9a80000,0xa9a8ac00,0x261f0000,0x2b6429a8,0x2b642c00,0x261f29a8,0xac002c00,0xac002c00,0xac002c00,0xac002c00,
0xab642c00,0xa61f29a8,0x261f0000,0x2b64a9a8,0xa9a82c00,0x29a80000,0x29a8ac00,0xa9a80000,0xa61f2c00,0x2b64a9a8,0xab640000,0x261f29a8,
0x2c00,0xac00,0x2c00,0xac00,0x261f2c00,0xab64a9a8,0x2b640000,0xa61f29a8,0x29a82c00,0xa9a80000,0xa9a8ac00,0x29a80000,
0x2b642c00,0x261f29a8,0xa61f0000,0xab64a9a8,0x2c002c00,0x2c002c00,0x2c002c00,0x2c002c00,0xab64ac00,0xa61fa9a8,0x261f0000,0x2b6429a8,
0x29a82c00,0xa9a80000,0xa9a8ac00,0x29a80000,0xa61fac00,0x2b6429a8,0xab640000,0x261fa9a8,0x2c00,0xac00,0x2c00,0xac00,
0x261fac00,0xab6429a8,0x2b640000,0xa61fa9a8,0xa9a82c00,0x29a80000,0x29a8ac00,0xa9a80000,0x2b64ac00,0x261fa9a8,0xa61f0000,0xab6429a8,
0,0,0,0,0xa61f0000,0xab64a9a8,0xab64ac00,0xa61fa9a8,0x29a80000,0x29a82c00,0xa9a80000,0xa9a8ac00,
0xab640000,0x261fa9a8,0x261f2c00,0xab64a9a8,0x2c000000,0xac000000,0x2c000000,0xac000000,0xab640000,0x261f29a8,0x261fac00,0xab6429a8,
0x29a80000,0x29a8ac00,0xa9a80000,0xa9a82c00,0xa61f0000,0xab6429a8,0xab642c00,0xa61f29a8,0xac002c00,0xac002c00,0xac002c00,0xac002c00,
0x2b64ac00,0x261fa9a8,0xa61f0000,0xab6429a8,0xa9a82c00,0x29a80000,0x29a8ac00,0xa9a80000,0x261fac00,0xab6429a8,0x2b640000,0xa61fa9a8,
0x2c00,0xac00,0x2c00,0xac00,0xa61fac00,0x2b6429a8,0xab640000,0x261fa9a8,0x29a82c00,0xa9a80000,0xa9a8ac00,0x29a80000,
0xab64ac00,0xa61fa9a8,0x261f0000,0x2b6429a8,0,0,0,0,0x261f0000,0x2b64a9a8,0x2b64ac00,0x261fa9a8,
0xa9a80000,0xa9a82c00,0x29a80000,0x29a8ac00,0x2b640000,0xa61fa9a8,0xa61f2c00,0x2b64a9a8,0xac000000,0x2c000000,0xac000000,0x2c000000,
0x2b640000,0xa61f29a8,0xa61fac00,0x2b6429a8,0xa9a80000,0xa9a8ac00,0x29a80000,0x29a82c00,0x261f0000,0x2b6429a8,0x2b642c00,0x261f29a8,
0,0,0,0,0x261f0000,0x2b6429a8,0x2b642c00,0x261f29a8,0xa9a80000,0xa9a8ac00,0x29a80000,0x29a82c00,
0x2b640000,0xa61f29a8,0xa61fac00,0x2b6429a8,0xac000000,0x2c000000,0xac000000,0x2c000000,0x2b640000,0xa61fa9a8,0xa61f2c00,0x2b64a9a8,
0xa9a80000,0xa9a82c00,0x29a80000,0x29a8ac00,0x261f0000,0x2b64a9a8,0x2b64ac00,0x261fa9a8,0x2c002c00,0x2c002c00,0x2c002c00,0x2c002c00,
0xab64ac00,0xa61fa9a8,0x261f0000,0x2b6429a8,0x29a82c00,0xa9a80000,0xa9a8ac00,0x29a80000,0xa61fac00,0x2b6429a8,0xab640000,0x261fa9a8,
0x2c00,0xac00,0x2c00,0xac00,0x261fac00,0xab6429a8,0x2b640000,0xa61fa9a8,0xa9a82c00,0x29a80000,0x29a8ac00,0xa9a80000,
0x2b64ac00,0x261fa9a8,0xa61f0000,0xab6429a8,0,0,0,0,0xa61f0000,0xab6429a8,0xab642c00,0xa61f29a8,
0x29a80000,0x29a8ac00,0xa9a80000,0xa9a82c00,0xab640000,0x261f29a8,0x261fac00,0xab6429a8,0x2c000000,0xac000000,0x2c000000,0xac000000,
0xab640000,0x261fa9a8,0x261f2c00,0xab64a9a8,0x29a80000,0x29a82c00,0xa9a80000,0xa9a8ac00,0xa61f0000,0xab64a9a8,0xab64ac00,0xa61fa9a8,
0xac002c00,0xac002c00,0xac002c00,0xac002c00,0x2b64ac00,0x261fa9a8,0xa61f0000,0xab6429a8,0xa9a82c00,0x29a80000,0x29a8ac00,0xa9a80000,
0x261fac00,0xab6429a8,0x2b640000,0xa61fa9a8,0x2c00,0xac00,0x2c00,0xac00,0xa61fac00,0x2b6429a8,0xab640000,0x261fa9a8,
0x29a82c00,0xa9a80000,0xa9a8ac00,0x29a80000,0xab64ac00,0xa61fa9a8,0x261f0000,0x2b6429a8,0x2bd92c00,0x2aa72b64,0x287229a8,0x223e261f,
0x2aa72c00,0xa23e261f,0xabd9a9a8,0xa872ab64,0x28722c00,0xabd9a61f,0x223ea9a8,0x2aa72b64,0x223e2c00,0xa872ab64,0x2aa729a8,0xabd9a61f,
0xa23e2c00,0x2872ab64,0xaaa729a8,0x2bd9a61f,0xa8722c00,0x2bd9a61f,0xa23ea9a8,0xaaa72b64,0xaaa72c00,0x223e261f,0x2bd9a9a8,0x2872ab64,
0xabd92c00,0xaaa72b64,0xa87229a8,0xa23e261f,0x223e0000,0x2872261f,0x2aa729a8,0x2bd92b64,0x28720000,0x2bd92b64,0x223e29a8,0xaaa7a61f,
0x2aa70000,0x223e2b64,0xabd9a9a8,0x2872a61f,0x2bd90000,0xaaa7261f,0x2872a9a8,0xa23e2b64,0x2bd90000,0xaaa7a61f,0x287229a8,0xa23eab64,
0x2aa70000,0x223eab64,0xabd929a8,0x2872261f,0x28720000,0x2bd9ab64,0x223ea9a8,0xaaa7261f,0x223e0000,0x2872a61f,0x2aa7a9a8,0x2bd9ab64,
0xabd92c00,0xaaa72b64,0xa87229a8,0xa23e261f,0xaaa72c00,0x223e261f,0x2bd9a9a8,0x2872ab64,0xa8722c00,0x2bd9a61f,0xa23ea9a8,0xaaa72b64,
0xa23e2c00,0x2872ab64,0xaaa729a8,0x2bd9a61f,0x223e2c00,0xa872ab64,0x2aa729a8,0xabd9a61f,0x28722c00,0xabd9a61f,0x223ea9a8,0x2aa72b64,
0x2aa72c00,0xa23e261f,0xabd9a9a8,0xa872ab64,0x2bd92c00,0x2aa72b64,0x287229a8,0x223e261f,0xa23e0000,0xa872261f,0xaaa729a8,0xabd92b64,
0xa8720000,0xabd92b64,0xa23e29a8,0x2aa7a61f,0xaaa70000,0xa23e2b64,0x2bd9a9a8,0xa872a61f,0xabd90000,0x2aa7261f,0xa872a9a8,0x223e2b64,
0xabd90000,0x2aa7a61f,0xa87229a8,0x223eab64,0xaaa70000,0xa23eab64,0x2bd929a8,0xa872261f,0xa8720000,0xabd9ab64,0xa23ea9a8,0x2aa7261f,
0xa23e0000,0xa872a61f,0xaaa7a9a8,0xabd9ab64,0xa23e0000,0xa872a61f,0xaaa7a9a8,0xabd9ab64,0xa8720000,0xabd9ab64,0xa23ea9a8,0x2aa7261f,
0xaaa70000,0xa23eab64,0x2bd929a8,0xa872261f,0xabd90000,0x2aa7a61f,0xa87229a8,0x223eab64,0xabd90000,0x2aa7261f,0xa872a9a8,0x223e2b64,
0xaaa70000,0xa23e2b64,0x2bd9a9a8,0xa872a61f,0xa8720000,0xabd92b64,0xa23e29a8,0x2aa7a61f,0xa23e0000,0xa872261f,0xaaa729a8,0xabd92b64,
0x2bd92c00,0x2aa72b64,0x287229a8,0x223e261f,0x2aa72c00,0xa23e261f,0xabd9a9a8,0xa872ab64,0x28722c00,0xabd9a61f,0x223ea9a8,0x2aa72b64,
0x223e2c00,0xa872ab64,0x2aa729a8,0xabd9a61f,0xa23e2c00,0x2872ab64,0xaaa729a8,0x2bd9a61f,0xa8722c00,0x2bd9a61f,0xa23ea9a8,0xaaa72b64,
0xaaa72c00,0x223e261f,0x2bd9a9a8,0x2872ab64,0xabd92c00,0xaaa72b64,0xa87229a8,0xa23e261f,0x223e0000,0x2872a61f,0x2aa7a9a8,0x2bd9ab64,
0x28720000,0x2bd9ab64,0x223ea9a8,0xaaa7261f,0x2aa70000,0x223eab64,0xabd929a8,0x2872261f,0x2bd90000,0xaaa7a61f,0x287229a8,0xa23eab64,
0x2bd90000,0xaaa7261f,0x2872a9a8,0xa23e2b64,0x2aa70000,0x223e2b64,0xabd9a9a8,0x2872a61f,0x28720000,0x2bd92b64,0x223e29a8,0xaaa7a61f,
0x223e0000,0x2872261f,0x2aa729a8,0x2bd92b64,0xabd92c00,0xaaa72b64,0xa87229a8,0xa23e261f,0xaaa72c00,0x223e261f,0x2bd9a9a8,0x2872ab64,
0xa8722c00,0x2bd9a61f,0xa23ea9a8,0xaaa72b64,0xa23e2c00,0x2872ab64,0xaaa729a8,0x2bd9a61f,0x223e2c00,0xa872ab64,0x2aa729a8,0xabd9a61f,
0x28722c00,0xabd9a61f,0x223ea9a8,0x2aa72b64,0x2aa72c00,0xa23e261f,0xabd9a9a8,0xa872ab64,0x2bd92c00,0x2aa72b64,0x287229a8,0x223e261f,
0xa23e0000,0xa872a61f,0xaaa7a9a8,0xabd9ab64,0x28720000,0x2bd92b64,0x223e29a8,0xaaa7a61f,0xaaa70000,0xa23eab64,0x2bd929a8,0xa872261f,
0x2bd90000,0xaaa7261f,0x2872a9a8,0xa23e2b64,0xabd90000,0x2aa7261f,0xa872a9a8,0x223e2b64,0x2aa70000,0x223eab64,0xabd929a8,0x2872261f,
0xa8720000,0xabd92b64,0xa23e29a8,0x2aa7a61f,0x223e0000,0x2872a61f,0x2aa7a9a8,0x2bd9ab64,0x2bd92c00,0x2aa72b64,0x287229a8,0x223e261f,
0xaaa7ac00,0x223ea61f,0x2bd929a8,0x28722b64,0x28722c00,0xabd9a61f,0x223ea9a8,0x2aa72b64,0xa23eac00,0x28722b64,0xaaa7a9a8,0x2bd9261f,
0xa23e2c00,0x2872ab64,0xaaa729a8,0x2bd9a61f,0x2872ac00,0xabd9261f,0x223e29a8,0x2aa7ab64,0xaaa72c00,0x223e261f,0x2bd9a9a8,0x2872ab64,
0x2bd9ac00,0x2aa7ab64,0x2872a9a8,0x223ea61f,0x223e0000,0x2872a61f,0x2aa7a9a8,0x2bd9ab64,0xa8720000,0xabd92b64,0xa23e29a8,0x2aa7a61f,
0x2aa70000,0x223eab64,0xabd929a8,0x2872261f,0xabd90000,0x2aa7261f,0xa872a9a8,0x223e2b64,0x2bd90000,0xaaa7261f,0x2872a9a8,0xa23e2b64,
0xaaa70000,0xa23eab64,0x2bd929a8,0xa872261f,0x28720000,0x2bd92b64,0x223e29a8,0xaaa7a61f,0xa23e0000,0xa872a61f,0xaaa7a9a8,0xabd9ab64,
0xabd92c00,0xaaa72b64,0xa87229a8,0xa23e261f,0x2aa7ac00,0xa23ea61f,0xabd929a8,0xa8722b64,0xa8722c00,0x2bd9a61f,0xa23ea9a8,0xaaa72b64,
0x223eac00,0xa8722b64,0x2aa7a9a8,0xabd9261f,0x223e2c00,0xa872ab64,0x2aa729a8,0xabd9a61f,0xa872ac00,0x2bd9261f,0xa23e29a8,0xaaa7ab64,
0x2aa72c00,0xa23e261f,0xabd9a9a8,0xa872ab64,0xabd9ac00,0xaaa7ab64,0xa872a9a8,0xa23ea61f,0xabd9ac00,0xaaa7ab64,0xa872a9a8,0xa23ea61f,
0x2aa72c00,0xa23e261f,0xabd9a9a8,0xa872ab64,0xa872ac00,0x2bd9261f,0xa23e29a8,0xaaa7ab64,0x223e2c00,0xa872ab64,0x2aa729a8,0xabd9a61f,
0x223eac00,0xa8722b64,0x2aa7a9a8,0xabd9261f,0xa8722c00,0x2bd9a61f,0xa23ea9a8,0xaaa72b64,0x2aa7ac00,0xa23ea61f,0xabd929a8,0xa8722b64,
0xabd92c00,0xaaa72b64,0xa87229a8,0xa23e261f,0xa23e0000,0xa872a61f,0xaaa7a9a8,0xabd9ab64,0x28720000,0x2bd92b64,0x223e29a8,0xaaa7a61f,
0xaaa70000,0xa23eab64,0x2bd929a8,0xa872261f,0x2bd90000,0xaaa7261f,0x2872a9a8,0xa23e2b64,0xabd90000,0x2aa7261f,0xa872a9a8,0x223e2b64,
0x2aa70000,0x223eab64,0xabd929a8,0x2872261f,0xa8720000,0xabd92b64,0xa23e29a8,0x2aa7a61f,0x223e0000,0x2872a61f,0x2aa7a9a8,0x2bd9ab64,
0x2bd9ac00,0x2aa7ab64,0x2872a9a8,0x223ea61f,0xaaa72c00,0x223e261f,0x2bd9a9a8,0x2872ab64,0x2872ac00,0xabd9261f,0x223e29a8,0x2aa7ab64,
0xa23e2c00,0x2872ab64,0xaaa729a8,0x2bd9a61f,0xa23eac00,0x28722b64,0xaaa7a9a8,0x2bd9261f,0x28722c00,0xabd9a61f,0x223ea9a8,0x2aa72b64,
0xaaa7ac00,0x223ea61f,0x2bd929a8,0x28722b64,0x2bd92c00,0x2aa72b64,0x287229a8,0x223e261f,0x223e0000,0x2872a61f,0x2aa7a9a8,0x2bd9ab64,
0xa8720000,0xabd92b64,0xa23e29a8,0x2aa7a61f,0x2aa70000,0x223eab64,0xabd929a8,0x2872261f,0xabd90000,0x2aa7261f,0xa872a9a8,0x223e2b64,
0x2bd90000,0xaaa7261f,0x2872a9a8,0xa23e2b64,0xaaa70000,0xa23eab64,0x2bd929a8,0xa872261f,0x28720000,0x2bd92b64,0x223e29a8,0xaaa7a61f,
0xa23e0000,0xa872a61f,0xaaa7a9a8,0xabd9ab64,0x27fe2800,0x96480000,0x273b2764,0xa2d7a21f,0x27ea27f6,0x9cb29a46,0x26dd270e,0xa41da38b,
0x27c327d9,0x9fc69e3e,0x266d26a7,0xa4c4a472,0x278827a8,0xa164a0a5,0x25ed262f,0xa55fa513,0x27c32800,0x9fc60000,0xa4c4a21f,0xa66da764,
0x25ed270e,0xa55fa38b,0xa73ba62f,0xa2d7a513,0x21642472,0xa788a6a7,0xa7fea7d9,0x16489e3e,0x9cb21a46,0xa7eaa7f6,0xa6dda7a8,0x241d20a5,
0x273b2800,0xa2d70000,0xa55fa764,0x25ed221f,0x1fc62513,0xa7c3a62f,0x1cb2a0a5,0x27ea27a8,0xa4c49e3e,0xa66da7d9,0x26dd2472,0x241d26a7,
0xa7fea70e,0x9648a38b,0x278827f6,0xa1641a46,0x266d2800,0xa4c40000,0x26dd221f,0x241d2764,0xa16420a5,0xa788a7a8,0x25ed27f6,0xa55f9a46,
0xa7fea6a7,0x1648a472,0xa2d71e3e,0xa73ba7d9,0x9fc6a62f,0x27c32513,0xa7eaa70e,0x1cb2a38b,0x255f2800,0xa5ed0000,0x21642764,0xa788a21f,
0xa66d9a46,0xa4c4a7f6,0xa7c3a38b,0x9fc6a70e,0xa41da7d9,0x26dd1e3e,0x9cb2a6a7,0x27ea2472,0x273b20a5,0x22d727a8,0x27fe2513,0x1648262f,
0x241d2800,0xa6dd0000,0xa7eaa21f,0x9cb2a764,0xa7fea38b,0x9648a70e,0x2164a513,0x2788262f,0x22d7a472,0x273b26a7,0x255f27d9,0xa5ed1e3e,
0x24c427f6,0xa66d1a46,0xa7c3a0a5,0x9fc6a7a8,0x21642800,0xa7880000,0x1648a764,0x27fe221f,0xa6dda62f,0x241da513,0x24c427a8,0xa66d20a5,
0x27ea1e3e,0x1cb227d9,0xa7c3a472,0x1fc6a6a7,0xa55f238b,0xa5eda70e,0x273b9a46,0x22d727f6,0x1cb22800,0xa7ea0000,0x27c3221f,0x9fc62764,
0xa2d7a7a8,0x273ba0a5,0xa7fe9a46,0x9648a7f6,0x255f26a7,0xa5ed2472,0x27889e3e,0x216427d9,0xa6dda513,0x241da62f,0xa66d238b,0xa4c4a70e,
0x96482800,0xa7fe0000,0xa2d72764,0xa73ba21f,0x1cb2a7f6,0x27ea1a46,0x241da70e,0x26dd238b,0x9fc627d9,0xa7c39e3e,0xa4c426a7,0xa66da472,
0x2164a7a8,0x278820a5,0x255fa62f,0x25ed2513,0x9fc62800,0xa7c30000,0xa66da21f,0x24c4a764,0x255fa70e,0x25ed238b,0x22d7262f,0xa73b2513,
0xa7882472,0xa164a6a7,0x1648a7d9,0x27fe9e3e,0x27ea9a46,0x9cb227f6,0xa41d27a8,0xa6dda0a5,0xa2d72800,0xa73b0000,0x25eda764,0x255f221f,
0x27c3a513,0x1fc6262f,0xa7ea20a5,0x1cb2a7a8,0xa66d9e3e,0x24c4a7d9,0x241d2472,0xa6dd26a7,0x1648270e,0xa7fe238b,0x2164a7f6,0x27889a46,
0xa4c42800,0xa66d0000,0x241d221f,0xa6dd2764,0x2788a0a5,0xa16427a8,0x255fa7f6,0x25ed1a46,0x1648a6a7,0x27fea472,0xa73b1e3e,0x22d7a7d9,
0xa7c3262f,0x9fc6a513,0x9cb2270e,0xa7ea238b,0xa5ed2800,0xa55f0000,0xa7882764,0xa164a21f,0x24c41a46,0xa66d27f6,0x1fc6238b,0xa7c3270e,
0x26dda7d9,0x241d1e3e,0x27eaa6a7,0x1cb22472,0xa2d7a0a5,0x273ba7a8,0x9648a513,0x27fea62f,0xa6dd2800,0xa41d0000,0x9cb2a21f,0x27eaa764,
0x1648238b,0xa7fe270e,0xa7882513,0x2164a62f,0x273ba472,0xa2d726a7,0xa5ed27d9,0xa55f1e3e,0x266da7f6,0x24c49a46,0x1fc620a5,0xa7c327a8,
0xa7882800,0xa1640000,0x27fea764,0x9648221f,0xa41d262f,0xa6dd2513,0x266da7a8,0x24c4a0a5,0x1cb21e3e,0xa7ea27d9,0x1fc6a472,0x27c3a6a7,
0x25eda38b,0xa55f270e,0xa2d71a46,0x273ba7f6,0xa7ea2800,0x9cb20000,0x9fc6221f,0xa7c32764,0xa73b27a8,0xa2d720a5,0x16481a46,0xa7fe27f6,
0xa5ed26a7,0xa55f2472,0x21649e3e,0xa78827d9,0xa41d2513,0xa6dd262f,0x24c4a38b,0xa66d270e,0xa7fe2800,0x16480000,0xa73b2764,0x22d7a21f,
0xa7ea27f6,0x1cb29a46,0xa6dd270e,0x241da38b,0xa7c327d9,0x1fc69e3e,0xa66d26a7,0x24c4a472,0xa78827a8,0x2164a0a5,0xa5ed262f,0x255fa513,
0xa7c32800,0x1fc60000,0x24c4a21f,0x266da764,0xa5ed270e,0x255fa38b,0x273ba62f,0x22d7a513,0xa1642472,0x2788a6a7,0x27fea7d9,0x96489e3e,
0x1cb21a46,0x27eaa7f6,0x26dda7a8,0xa41d20a5,0xa73b2800,0x22d70000,0x255fa764,0xa5ed221f,0x9fc62513,0x27c3a62f,0x9cb2a0a5,0xa7ea27a8,
0x24c49e3e,0x266da7d9,0xa6dd2472,0xa41d26a7,0x27fea70e,0x1648a38b,0xa78827f6,0x21641a46,0xa66d2800,0x24c40000,0xa6dd221f,0xa41d2764,
0x216420a5,0x2788a7a8,0xa5ed27f6,0x255f9a46,0x27fea6a7,0x9648a472,0x22d71e3e,0x273ba7d9,0x1fc6a62f,0xa7c32513,0x27eaa70e,0x9cb2a38b,
0xa55f2800,0x25ed0000,0xa1642764,0x2788a21f,0x266d9a46,0x24c4a7f6,0x27c3a38b,0x1fc6a70e,0x241da7d9,0xa6dd1e3e,0x1cb2a6a7,0xa7ea2472,
0xa73b20a5,0xa2d727a8,0xa7fe2513,0x9648262f,0xa41d2800,0x26dd0000,0x27eaa21f,0x1cb2a764,0x27fea38b,0x1648a70e,0xa164a513,0xa788262f,
0xa2d7a472,0xa73b26a7,0xa55f27d9,0x25ed1e3e,0xa4c427f6,0x266d1a46,0x27c3a0a5,0x1fc6a7a8,0xa1642800,0x27880000,0x9648a764,0xa7fe221f,
0x26dda62f,0xa41da513,0xa4c427a8,0x266d20a5,0xa7ea1e3e,0x9cb227d9,0x27c3a472,0x9fc6a6a7,0x255f238b,0x25eda70e,0xa73b9a46,0xa2d727f6,
0x9cb22800,0x27ea0000,0xa7c3221f,0x1fc62764,0x22d7a7a8,0xa73ba0a5,0x27fe9a46,0x1648a7f6,0xa55f26a7,0x25ed2472,0xa7889e3e,0xa16427d9,
0x26dda513,0xa41da62f,0x266d238b,0x24c4a70e,0x16482800,0x27fe0000,0x22d72764,0x273ba21f,0x9cb2a7f6,0xa7ea1a46,0xa41da70e,0xa6dd238b,
0x1fc627d9,0x27c39e3e,0x24c426a7,0x266da472,0xa164a7a8,0xa78820a5,0xa55fa62f,0xa5ed2513,0x1fc62800,0x27c30000,0x266da21f,0xa4c4a764,
0xa55fa70e,0xa5ed238b,0xa2d7262f,0x273b2513,0x27882472,0x2164a6a7,0x9648a7d9,0xa7fe9e3e,0xa7ea9a46,0x1cb227f6,0x241d27a8,0x26dda0a5,
0x22d72800,0x273b0000,0xa5eda764,0xa55f221f,0xa7c3a513,0x9fc6262f,0x27ea20a5,0x9cb2a7a8,0x266d9e3e,0xa4c4a7d9,0xa41d2472,0x26dd26a7,
0x9648270e,0x27fe238b,0xa164a7f6,0xa7889a46,0x24c42800,0x266d0000,0xa41d221f,0x26dd2764,0xa788a0a5,0x216427a8,0xa55fa7f6,0xa5ed1a46,
0x9648a6a7,0xa7fea472,0x273b1e3e,0xa2d7a7d9,0x27c3262f,0x1fc6a513,0x1cb2270e,0x27ea238b,0x25ed2800,0x255f0000,0x27882764,0x2164a21f,
0xa4c41a46,0x266d27f6,0x9fc6238b,0x27c3270e,0xa6dda7d9,0xa41d1e3e,0xa7eaa6a7,0x9cb22472,0x22d7a0a5,0xa73ba7a8,0x1648a513,0xa7fea62f,
0x26dd2800,0x241d0000,0x1cb2a21f,0xa7eaa764,0x9648238b,0x27fe270e,0x27882513,0xa164a62f,0xa73ba472,0x22d726a7,0x25ed27d9,0x255f1e3e,
0xa66da7f6,0xa4c49a46,0x9fc620a5,0x27c327a8,0x27882800,0x21640000,0xa7fea764,0x1648221f,0x241d262f,0x26dd2513,0xa66da7a8,0xa4c4a0a5,
0x9cb21e3e,0x27ea27d9,0x9fc6a472,0xa7c3a6a7,0xa5eda38b,0x255f270e,0x22d71a46,0xa73ba7f6,0x27ea2800,0x1cb20000,0x1fc6221f,0x27c32764,
0x273b27a8,0x22d720a5,0x96481a46,0x27fe27f6,0x25ed26a7,0x255f2472,0xa1649e3e,0x278827d9,0x241d2513,0x26dd262f,0xa4c4a38b,0x266d270e,
0x255f25a8,0xa5eda5a8,0x2164221f,0xa788a764,0x24c42513,0xa66da62f,0x1fc620a5,0xa7c3a7a8,0x241d2472,0xa6dda6a7,0x1cb21e3e,0xa7eaa7d9,
0x22d7238b,0xa73ba70e,0x16481a46,0xa7fea7f6,0xa41da5a8,0x26dd25a8,0x27ea2764,0x1cb2221f,0x9648a0a5,0x27fe27a8,0x278827f6,0xa1649a46,
0x22d71e3e,0x273b27d9,0x255f26a7,0xa5eda472,0x266d2513,0x24c4262f,0x1fc6238b,0xa7c3a70e,0x216425a8,0xa788a5a8,0x1648a21f,0x27fe2764,
0xa41d9a46,0xa6dda7f6,0x266d238b,0x24c4270e,0xa7eaa6a7,0x9cb2a472,0x27c327d9,0x9fc61e3e,0xa5eda7a8,0x255f20a5,0x22d7262f,0xa73ba513,
0x9cb2a5a8,0x27ea25a8,0xa7c3a764,0x1fc6a21f,0x273b238b,0x22d7270e,0x9648a513,0x27fe262f,0x255f27d9,0xa5ed9e3e,0x27882472,0x216426a7,
0xa41d1a46,0xa6dda7f6,0x24c427a8,0xa66da0a5,0x964825a8,0xa7fea5a8,0xa2d7221f,0xa73ba764,0xa7eaa62f,0x1cb2a513,0xa6dda7a8,0x241da0a5,
0x1fc6a472,0x27c326a7,0x24c49e3e,0x266d27d9,0x2788270e,0xa164238b,0x25ed27f6,0xa55f1a46,0x1fc6a5a8,0x27c325a8,0x266d2764,0xa4c4221f,
0x25ed27a8,0xa55f20a5,0xa73b9a46,0xa2d7a7f6,0xa7889e3e,0xa164a7d9,0x1648a6a7,0x27fe2472,0x1cb2a62f,0x27ea2513,0x26dd270e,0xa41d238b,
0xa2d725a8,0xa73ba5a8,0x25eda21f,0x255f2764,0x9fc6a7f6,0x27c31a46,0x9cb2270e,0xa7eaa38b,0x266d26a7,0xa4c42472,0xa41da7d9,0x26dd9e3e,
0xa7fea0a5,0x9648a7a8,0x27882513,0xa164262f,0x24c4a5a8,0x266d25a8,0xa41da764,0x26dda21f,0xa164270e,0xa788a38b,0x25ed262f,0xa55f2513,
0x1648a7d9,0x27fe1e3e,0xa73ba472,0x22d7a6a7,0x1fc627f6,0xa7c31a46,0x27ea20a5,0x9cb227a8,0xa5ed25a8,0xa55fa5a8,0xa788221f,0xa164a764,
0x266da513,0x24c4262f,0x27c3a0a5,0x1fc627a8,0xa6dd2472,0xa41da6a7,0xa7ea1e3e,0x9cb2a7d9,0x273ba38b,0x22d7270e,0x27fe9a46,0x164827f6,
0x26dda5a8,0x241d25a8,0x1cb22764,0xa7ea221f,0xa7fe20a5,0x9648a7a8,0x2164a7f6,0x27881a46,0x273b1e3e,0xa2d727d9,0xa5ed26a7,0xa55fa472,
0xa4c4a513,0x266da62f,0x27c3a38b,0x1fc6270e,0xa78825a8,0xa164a5a8,0x27fea21f,0x96482764,0x26dd1a46,0xa41d27f6,0xa4c4a38b,0x266da70e,
0x9cb2a6a7,0x27eaa472,0x9fc627d9,0xa7c31e3e,0xa55f27a8,0xa5eda0a5,0x273ba62f,0x22d72513,0x27eaa5a8,0x1cb225a8,0x1fc6a764,0x27c3a21f,
0xa2d7a38b,0x273ba70e,0xa7fe2513,0x9648a62f,0xa5ed27d9,0xa55f9e3e,0x21642472,0xa78826a7,0x26dd9a46,0xa41d27f6,0x266da7a8,0x24c420a5,
0xa7fe25a8,0x1648a5a8,0xa73b221f,0x22d7a764,0x9cb2262f,0xa7ea2513,0xa41d27a8,0xa6dd20a5,0x27c3a472,0x9fc626a7,0x266d9e3e,0xa4c427d9,
0x2164a70e,0x2788a38b,0x255fa7f6,0x25ed9a46,0x27c3a5a8,0x9fc625a8,0xa4c42764,0xa66d221f,0x255fa7a8,0x25eda0a5,0x22d71a46,0xa73b27f6,
0xa1649e3e,0x2788a7d9,0x27fea6a7,0x96482472,0xa7ea262f,0x1cb2a513,0x241da70e,0x26dda38b,0xa73b25a8,0x22d7a5a8,0x255fa21f,0xa5ed2764,
0xa7c327f6,0x9fc69a46,0x27eaa70e,0x9cb2238b,0xa4c426a7,0xa66d2472,0x26dda7d9,0x241d9e3e,0x164820a5,0xa7fe27a8,0x2164a513,0x2788a62f,
0x266da5a8,0xa4c425a8,0x26dda764,0x241da21f,0x2788a70e,0xa164238b,0x255fa62f,0x25eda513,0x27fea7d9,0x96481e3e,0x22d7a472,0x273ba6a7,
0x27c3a7f6,0x1fc69a46,0x1cb2a0a5,0x27eaa7a8,0xa55f25a8,0x25eda5a8,0xa164221f,0x2788a764,0xa4c42513,0x266da62f,0x9fc620a5,0x27c3a7a8,
0xa41d2472,0x26dda6a7,0x9cb21e3e,0x27eaa7d9,0xa2d7238b,0x273ba70e,0x96481a46,0x27fea7f6,0x241da5a8,0xa6dd25a8,0xa7ea2764,0x9cb2221f,
0x1648a0a5,0xa7fe27a8,0xa78827f6,0x21649a46,0xa2d71e3e,0xa73b27d9,0xa55f26a7,0x25eda472,0xa66d2513,0xa4c4262f,0x9fc6238b,0x27c3a70e,
0xa16425a8,0x2788a5a8,0x9648a21f,0xa7fe2764,0x241d9a46,0x26dda7f6,0xa66d238b,0xa4c4270e,0x27eaa6a7,0x1cb2a472,0xa7c327d9,0x1fc61e3e,
0x25eda7a8,0xa55f20a5,0xa2d7262f,0x273ba513,0x1cb2a5a8,0xa7ea25a8,0x27c3a764,0x9fc6a21f,0xa73b238b,0xa2d7270e,0x1648a513,0xa7fe262f,
0xa55f27d9,0x25ed9e3e,0xa7882472,0xa16426a7,0x241d1a46,0x26dda7f6,0xa4c427a8,0x266da0a5,0x164825a8,0x27fea5a8,0x22d7221f,0x273ba764,
0x27eaa62f,0x9cb2a513,0x26dda7a8,0xa41da0a5,0x9fc6a472,0xa7c326a7,0xa4c49e3e,0xa66d27d9,0xa788270e,0x2164238b,0xa5ed27f6,0x255f1a46,
0x9fc6a5a8,0xa7c325a8,0xa66d2764,0x24c4221f,0xa5ed27a8,0x255f20a5,0x273b9a46,0x22d7a7f6,0x27889e3e,0x2164a7d9,0x9648a6a7,0xa7fe2472,
0x9cb2a62f,0xa7ea2513,0xa6dd270e,0x241d238b,0x22d725a8,0x273ba5a8,0xa5eda21f,0xa55f2764,0x1fc6a7f6,0xa7c31a46,0x1cb2270e,0x27eaa38b,
0xa66d26a7,0x24c42472,0x241da7d9,0xa6dd9e3e,0x27fea0a5,0x1648a7a8,0xa7882513,0x2164262f,0xa4c4a5a8,0xa66d25a8,0x241da764,0xa6dda21f,
0x2164270e,0x2788a38b,0xa5ed262f,0x255f2513,0x9648a7d9,0xa7fe1e3e,0x273ba472,0xa2d7a6a7,0x9fc627f6,0x27c31a46,0xa7ea20a5,0x1cb227a8,
0x25ed25a8,0x255fa5a8,0x2788221f,0x2164a764,0xa66da513,0xa4c4262f,0xa7c3a0a5,0x9fc627a8,0x26dd2472,0x241da6a7,0x27ea1e3e,0x1cb2a7d9,
0xa73ba38b,0xa2d7270e,0xa7fe9a46,0x964827f6,0xa6dda5a8,0xa41d25a8,0x9cb22764,0x27ea221f,0x27fe20a5,0x1648a7a8,0xa164a7f6,0xa7881a46,
0xa73b1e3e,0x22d727d9,0x25ed26a7,0x255fa472,0x24c4a513,0xa66da62f,0xa7c3a38b,0x9fc6270e,0x278825a8,0x2164a5a8,0xa7fea21f,0x16482764,
0xa6dd1a46,0x241d27f6,0x24c4a38b,0xa66da70e,0x1cb2a6a7,0xa7eaa472,0x1fc627d9,0x27c31e3e,0x255f27a8,0x25eda0a5,0xa73ba62f,0xa2d72513,
0xa7eaa5a8,0x9cb225a8,0x9fc6a764,0xa7c3a21f,0x22d7a38b,0xa73ba70e,0x27fe2513,0x1648a62f,0x25ed27d9,0x255f9e3e,0xa1642472,0x278826a7,
0xa6dd9a46,0x241d27f6,0xa66da7a8,0xa4c420a5,0x27fe25a8,0x9648a5a8,0x273b221f,0xa2d7a764,0x1cb2262f,0x27ea2513,0x241d27a8,0x26dd20a5,
0xa7c3a472,0x1fc626a7,0xa66d9e3e,0x24c427d9,0xa164a70e,0xa788a38b,0xa55fa7f6,0xa5ed9a46,0xa7c3a5a8,0x1fc625a8,0x24c42764,0x266d221f,
0xa55fa7a8,0xa5eda0a5,0xa2d71a46,0x273b27f6,0x21649e3e,0xa788a7d9,0xa7fea6a7,0x16482472,0x27ea262f,0x9cb2a513,0xa41da70e,0xa6dda38b,
0x273b25a8,0xa2d7a5a8,0xa55fa21f,0x25ed2764,0x27c327f6,0x1fc69a46,0xa7eaa70e,0x1cb2238b,0x24c426a7,0x266d2472,0xa6dda7d9,0xa41d9e3e,
0x964820a5,0x27fe27a8,0xa164a513,0xa788a62f,0xa66da5a8,0x24c425a8,0xa6dda764,0xa41da21f,0xa788a70e,0x2164238b,0xa55fa62f,0xa5eda513,
0xa7fea7d9,0x16481e3e,0xa2d7a472,0xa73ba6a7,0xa7c3a7f6,0x9fc69a46,0x9cb2a0a5,0xa7eaa7a8,
};

#define PROF(slot) do {} while (0)
#define PROF3(slot) do {} while (0)
#define PROF2(slot) do {} while (0)

__device__ __forceinline__ uint32_t smem_u32(const void* p) { return (uint32_t)__cvta_generic_to_shared(p); }

__device__ __forceinline__ void mbar_init(uint32_t a, uint32_t c) {
  asm volatile("mbarrier.init.shared::cta.b64 [%0], %1;\n" ::"r"(a), "r"(c) : "memory");
}
__device__ __forceinline__ void mbar_expect_tx(uint32_t a, uint32_t bytes) {
  asm volatile("mbarrier.arrive.expect_tx.shared::cta.b64 _, [%0], %1;\n" ::"r"(a), "r"(bytes) : "memory");
}
__device__ __forceinline__ void mbar_arrive_cluster(uint32_t cluster_addr) {
  asm volatile("mbarrier.arrive.shared::cluster.b64 _, [%0];\n" ::"r"(cluster_addr) : "memory");
}
__device__ __forceinline__ void mbar_arrive_cluster_n(uint32_t cluster_addr, uint32_t n) {
  asm volatile("mbarrier.arrive.shared::cluster.b64 _, [%0], %1;\n" ::"r"(cluster_addr), "r"(n) : "memory");
}
__device__ __forceinline__ bool mbar_try(uint32_t a, uint32_t parity) {
  uint32_t ok;
  asm volatile("{\n.reg .pred p;\nmbarrier.try_wait.parity.shared::cta.b64 p, [%1], %2;\nselp.u32 %0, 1, 0, p;\n}\n"
               : "=r"(ok) : "r"(a), "r"(parity) : "memory");
  return ok;
}
__device__ __forceinline__ void mbar_wait(uint32_t a, uint32_t parity) {
  if (mbar_try(a, parity)) return;
#pragma unroll 1
  for (int n = 0; n < SPIN_LIMIT; n++)
    if (mbar_try(a, parity)) break;
}
__device__ __forceinline__ void mbar_wait_idle(uint32_t a, uint32_t parity) {
#pragma unroll 1
  for (int n = 0; n < SPIN_LIMIT; n++) {
    uint32_t ok;
    asm volatile("{\n.reg .pred p;\nmbarrier.try_wait.parity.shared::cta.b64 p, [%1], %2, %3;\nselp.u32 %0, 1, 0, p;\n}\n"
                 : "=r"(ok) : "r"(a), "r"(parity), "r"(4000) : "memory");
    if (ok) break;
  }
}
__device__ __forceinline__ bool elect_one() {
  uint32_t p;
  asm volatile("{\n.reg .pred P;\nelect.sync _|P, 0xffffffff;\nselp.u32 %0, 1, 0, P;\n}\n" : "=r"(p));
  return p;
}
__device__ __forceinline__ uint32_t mapa(uint32_t a, uint32_t rank) {
  uint32_t r;
  asm volatile("mapa.shared::cluster.u32 %0, %1, %2;\n" : "=r"(r) : "r"(a), "r"(rank));
  return r;
}
__device__ __forceinline__ void nb_sync(int id, int n) { asm volatile("bar.sync %0, %1;\n" ::"r"(id), "r"(n) : "memory"); }
__device__ __forceinline__ void nb_arrive(int id, int n) { asm volatile("bar.arrive %0, %1;\n" ::"r"(id), "r"(n) : "memory"); }
__device__ __forceinline__ void cluster_sync_all() {
  asm volatile("barrier.cluster.arrive.relaxed.aligned;\nbarrier.cluster.wait.aligned;\n" ::: "memory");
}
__device__ __forceinline__ void fence_async_smem() { asm volatile("fence.proxy.async.shared::cta;\n" ::: "memory"); }
__device__ __forceinline__ void fence_async_all() { asm volatile("fence.proxy.async.global;\n" ::: "memory"); }

__device__ __forceinline__ void tma_load_3d(uint32_t dst, const CUtensorMap* tm, uint32_t bar, int c0, int c1, int c2) {
  asm volatile(
      "cp.async.bulk.tensor.3d.shared::cluster.global.mbarrier::complete_tx::bytes [%0], [%1, {%3, %4, %5}], [%2];\n"
      ::"r"(dst), "l"(tm), "r"(bar), "r"(c0), "r"(c1), "r"(c2) : "memory");
}
__device__ __forceinline__ void tma_load_4d(uint32_t dst, const CUtensorMap* tm, uint32_t bar, int c0, int c1, int c2, int c3) {
  asm volatile(
      "cp.async.bulk.tensor.4d.shared::cluster.global.mbarrier::complete_tx::bytes [%0], [%1, {%3, %4, %5, %6}], [%2];\n"
      ::"r"(dst), "l"(tm), "r"(bar), "r"(c0), "r"(c1), "r"(c2), "r"(c3) : "memory");
}
__device__ __forceinline__ void tma_load_3d_mc(uint32_t dst, const CUtensorMap* tm, uint32_t bar, int c0, int c1, int c2) {
  asm volatile(
      "cp.async.bulk.tensor.3d.shared::cluster.global.mbarrier::complete_tx::bytes.multicast::cluster [%0], [%1, {%3, %4, %5}], [%2], %6;\n"
      ::"r"(dst), "l"(tm), "r"(bar), "r"(c0), "r"(c1), "r"(c2), "h"((uint16_t)3) : "memory");
}
__device__ __forceinline__ void tma_load_5d(uint32_t dst, const CUtensorMap* tm, uint32_t bar, int c0, int c4) {
  asm volatile(
      "cp.async.bulk.tensor.5d.shared::cluster.global.mbarrier::complete_tx::bytes [%0], [%1, {%3, %5, %5, %5, %4}], [%2];\n"
      ::"r"(dst), "l"(tm), "r"(bar), "r"(c0), "r"(c4), "r"(0) : "memory");
}
__device__ __forceinline__ void bulk_load(uint32_t dst, const void* src, uint32_t bytes, uint32_t bar) {
  asm volatile("cp.async.bulk.shared::cluster.global.mbarrier::complete_tx::bytes [%0], [%1], %2, [%3];\n"
               ::"r"(dst), "l"(src), "r"(bytes), "r"(bar) : "memory");
}
__device__ __forceinline__ void bulk_commit() { asm volatile("cp.async.bulk.commit_group;\n" ::: "memory"); }
__device__ __forceinline__ void bulk_wait0() { asm volatile("cp.async.bulk.wait_group 0;\n" ::: "memory"); }
__device__ __forceinline__ void prefetch_tmap(const CUtensorMap* tm) {
  asm volatile("prefetch.tensormap [%0];\n" ::"l"(tm) : "memory");
}

__device__ __forceinline__ void wg_fence() { asm volatile("wgmma.fence.sync.aligned;\n" ::: "memory"); }
__device__ __forceinline__ void wg_commit() { asm volatile("wgmma.commit_group.sync.aligned;\n" ::: "memory"); }
template <int N> __device__ __forceinline__ void wg_wait() {
  asm volatile("wgmma.wait_group.sync.aligned %0;\n" ::"n"(N) : "memory");
}
__device__ __forceinline__ uint64_t mkdesc(uint32_t addr, uint32_t lbo, uint32_t sbo, uint32_t swz) {
  return (uint64_t)((addr & 0x3FFFF) >> 4) | ((uint64_t)(lbo >> 4) << 16) | ((uint64_t)(sbo >> 4) << 32) |
         ((uint64_t)swz << 62);
}

#define R4(d, o) "+f"(d[o + 0]), "+f"(d[o + 1]), "+f"(d[o + 2]), "+f"(d[o + 3])
#define R8(d, o) R4(d, o), R4(d, o + 4)
#define R16(d, o) R8(d, o), R8(d, o + 8)
#define R32(d, o) R16(d, o), R16(d, o + 16)
#define R64(d, o) R32(d, o), R32(d, o + 32)

__device__ __forceinline__ void wgmma_n192(float (&d)[96], uint64_t da, uint64_t db, uint32_t acc) {
  asm volatile(
      "{\n.reg .pred p;\nsetp.ne.u32 p, %98, 0;\n"
      "wgmma.mma_async.sync.aligned.m64n192k16.f32.bf16.bf16 "
      "{%0,%1,%2,%3,%4,%5,%6,%7,%8,%9,%10,%11,%12,%13,%14,%15,%16,%17,%18,%19,%20,%21,%22,%23,%24,%25,%26,%27,%28,%29,%30,%31,"
      "%32,%33,%34,%35,%36,%37,%38,%39,%40,%41,%42,%43,%44,%45,%46,%47,%48,%49,%50,%51,%52,%53,%54,%55,%56,%57,%58,%59,%60,%61,%62,%63,"
      "%64,%65,%66,%67,%68,%69,%70,%71,%72,%73,%74,%75,%76,%77,%78,%79,%80,%81,%82,%83,%84,%85,%86,%87,%88,%89,%90,%91,%92,%93,%94,%95}, "
      "%96, %97, p, 1, 1, 0, 1;\n}\n"
      : R64(d, 0), R32(d, 64)
      : "l"(da), "l"(db), "r"(acc));
}
__device__ __forceinline__ void wgmma_n128(float (&d)[64], uint64_t da, uint64_t db, uint32_t acc) {
  asm volatile(
      "{\n.reg .pred p;\nsetp.ne.u32 p, %66, 0;\n"
      "wgmma.mma_async.sync.aligned.m64n128k16.f32.bf16.bf16 "
      "{%0,%1,%2,%3,%4,%5,%6,%7,%8,%9,%10,%11,%12,%13,%14,%15,%16,%17,%18,%19,%20,%21,%22,%23,%24,%25,%26,%27,%28,%29,%30,%31,"
      "%32,%33,%34,%35,%36,%37,%38,%39,%40,%41,%42,%43,%44,%45,%46,%47,%48,%49,%50,%51,%52,%53,%54,%55,%56,%57,%58,%59,%60,%61,%62,%63}, "
      "%64, %65, p, 1, 1, 0, 1;\n}\n"
      : R64(d, 0)
      : "l"(da), "l"(db), "r"(acc));
}
template <int N> __device__ __forceinline__ void fence_regs(float (&d)[N]) {
#pragma unroll
  for (int i = 0; i < N; i++) asm volatile("" : "+f"(d[i])::"memory");
}

__device__ __forceinline__ void mma16816(float (&d)[4], uint32_t a0, uint32_t a1, uint32_t a2, uint32_t a3, uint32_t b0,
                                         uint32_t b1) {
  asm("mma.sync.aligned.m16n8k16.row.col.f32.bf16.bf16.f32 {%0,%1,%2,%3}, {%4,%5,%6,%7}, {%8,%9}, {%0,%1,%2,%3};\n"
      : "+f"(d[0]), "+f"(d[1]), "+f"(d[2]), "+f"(d[3])
      : "r"(a0), "r"(a1), "r"(a2), "r"(a3), "r"(b0), "r"(b1));
}
__device__ __forceinline__ void mma16816_z(float (&d)[4], uint32_t a0, uint32_t a1, uint32_t a2, uint32_t a3, uint32_t b0,
                                           uint32_t b1) {
  asm("mma.sync.aligned.m16n8k16.row.col.f32.bf16.bf16.f32 {%0,%1,%2,%3}, {%4,%5,%6,%7}, {%8,%9}, {%10,%10,%10,%10};\n"
      : "=f"(d[0]), "=f"(d[1]), "=f"(d[2]), "=f"(d[3])
      : "r"(a0), "r"(a1), "r"(a2), "r"(a3), "r"(b0), "r"(b1), "f"(0.f));
}
__device__ __forceinline__ void ldsm4t(uint32_t (&r)[4], uint32_t a) {
  asm volatile("ldmatrix.sync.aligned.m8n8.x4.trans.shared.b16 {%0,%1,%2,%3}, [%4];\n"
               : "=r"(r[0]), "=r"(r[1]), "=r"(r[2]), "=r"(r[3]) : "r"(a) : "memory");
}
__device__ __forceinline__ void ldsm2t(uint32_t& r0, uint32_t& r1, uint32_t a) {
  asm volatile("ldmatrix.sync.aligned.m8n8.x2.trans.shared.b16 {%0,%1}, [%2];\n" : "=r"(r0), "=r"(r1) : "r"(a) : "memory");
}
__device__ __forceinline__ void st_async128(uint32_t a, uint32_t bar, uint32_t x, uint32_t y, uint32_t z, uint32_t w) {
  asm volatile("st.async.weak.shared::cluster.mbarrier::complete_tx::bytes.v4.b32 [%0], {%2,%3,%4,%5}, [%1];\n"
               ::"r"(a), "r"(bar), "r"(x), "r"(y), "r"(z), "r"(w) : "memory");
}
__device__ __forceinline__ void mbar_arrive(uint32_t a) {
  asm volatile("mbarrier.arrive.shared::cta.b64 _, [%0];\n" ::"r"(a) : "memory");
}
__device__ __forceinline__ void stsm4(uint32_t a, uint32_t r0, uint32_t r1, uint32_t r2, uint32_t r3) {
  asm volatile("stmatrix.sync.aligned.m8n8.x4.shared.b16 [%0], {%1,%2,%3,%4};\n"
               ::"r"(a), "r"(r0), "r"(r1), "r"(r2), "r"(r3) : "memory");
}
__device__ __forceinline__ void stsm4t(uint32_t a, uint32_t r0, uint32_t r1, uint32_t r2, uint32_t r3) {
  asm volatile("stmatrix.sync.aligned.m8n8.x4.trans.shared.b16 [%0], {%1,%2,%3,%4};\n"
               ::"r"(a), "r"(r0), "r"(r1), "r"(r2), "r"(r3) : "memory");
}
__device__ __forceinline__ uint2 lds64(uint32_t a) {
  uint2 v;
  asm volatile("ld.shared.v2.u32 {%0,%1}, [%2];\n" : "=r"(v.x), "=r"(v.y) : "r"(a));
  return v;
}
__device__ __forceinline__ uint4 lds128(uint32_t a) {
  uint4 v;
  asm volatile("ld.shared.v4.u32 {%0,%1,%2,%3}, [%4];\n" : "=r"(v.x), "=r"(v.y), "=r"(v.z), "=r"(v.w) : "r"(a) : "memory");
  return v;
}
__device__ __forceinline__ void sts128(uint32_t a, uint32_t x, uint32_t y, uint32_t z, uint32_t w) {
  asm volatile("st.shared.v4.u32 [%0], {%1,%2,%3,%4};\n" ::"r"(a), "r"(x), "r"(y), "r"(z), "r"(w) : "memory");
}
__device__ __forceinline__ uint32_t pack_bf16(float lo, float hi) {
  uint32_t r;
  asm("cvt.rn.bf16x2.f32 %0, %1, %2;\n" : "=r"(r) : "f"(hi), "f"(lo));
  return r;
}
__device__ __forceinline__ uint32_t bmul2(uint32_t a, uint32_t b) {
  uint32_t r;
  asm("mul.rn.bf16x2 %0, %1, %2;\n" : "=r"(r) : "r"(a), "r"(b));
  return r;
}
__device__ __forceinline__ uint32_t bmax2(uint32_t a, uint32_t b) {
  uint32_t r;
  asm("max.bf16x2 %0, %1, %2;\n" : "=r"(r) : "r"(a), "r"(b));
  return r;
}
__device__ __forceinline__ uint32_t bfma2(uint32_t a, uint32_t b, uint32_t c) {
  uint32_t r;
  asm("fma.rn.bf16x2 %0, %1, %2, %3;\n" : "=r"(r) : "r"(a), "r"(b), "r"(c));
  return r;
}
__device__ __forceinline__ uint32_t badd2(uint32_t a, uint32_t b) {
  uint32_t r;
  asm("add.rn.bf16x2 %0, %1, %2;\n" : "=r"(r) : "r"(a), "r"(b));
  return r;
}
__device__ __forceinline__ void prefetch_l2(const void* p) { asm volatile("prefetch.global.L2 [%0];\n" ::"l"(p)); }
__device__ __forceinline__ void cp_async16n(uint32_t dst, const void* src) {
  asm volatile("cp.async.cg.shared.global [%0], [%1], 16;\n" ::"r"(dst), "l"(src) : "memory");
}
__device__ __forceinline__ void cp_async16(uint32_t dst, const void* src, uint32_t srcbytes) {
  asm volatile("cp.async.cg.shared.global.L2::256B [%0], [%1], 16, %2;\n" ::"r"(dst), "l"(src), "r"(srcbytes) : "memory");
}
__device__ __forceinline__ uint32_t ld_acquire(const uint32_t* p) {
  uint32_t v;
  asm volatile("ld.acquire.gpu.global.u32 %0, [%1];\n" : "=r"(v) : "l"(p) : "memory");
  return v;
}
__device__ __forceinline__ uint32_t ld_relaxed(const uint32_t* p) {
  uint32_t v;
  asm volatile("ld.relaxed.gpu.global.u32 %0, [%1];\n" : "=r"(v) : "l"(p) : "memory");
  return v;
}
__device__ __forceinline__ void st_release(uint32_t* p, uint32_t v) {
  asm volatile("st.release.gpu.global.u32 [%0], %1;\n" ::"l"(p), "r"(v) : "memory");
}
__device__ __forceinline__ void wait_flag(const uint32_t* p, uint32_t want) {
  int n = 0;
  while (ld_relaxed(p) != want && ++n < SPIN_LIMIT) __nanosleep(40);
  (void)ld_acquire(p);
}

struct Params {
  const __nv_bfloat16* x;
  const __nv_bfloat16* w;
  const __nv_bfloat16* q;
  const __nv_bfloat16* k;
  const __nv_bfloat16* v;
  const __nv_bfloat16* shift_k;
  const __nv_bfloat16* ssm_k;
  const __nv_bfloat16* ssm_D;
  const __nv_bfloat16* wo;
  __nv_bfloat16* out;
};

__device__ __forceinline__ uint32_t lds32(uint32_t a) {
  uint32_t v;
  asm volatile("ld.shared.u32 %0, [%1];\n" : "=r"(v) : "r"(a));
  return v;
}
#define W4(d, o) "=f"(d[o + 0]), "=f"(d[o + 1]), "=f"(d[o + 2]), "=f"(d[o + 3])
#define W8(d, o) W4(d, o), W4(d, o + 4)
#define W16(d, o) W8(d, o), W8(d, o + 8)
#define U4(c, d, o) c(d[o + 0]), c(d[o + 1]), c(d[o + 2]), c(d[o + 3])
#define U8(c, d, o) U4(c, d, o), U4(c, d, o + 4)
#define U16(c, d, o) U8(c, d, o), U8(c, d, o + 8)
#define U32(c, d, o) U16(c, d, o), U16(c, d, o + 16)
#define D32 "{%0,%1,%2,%3,%4,%5,%6,%7,%8,%9,%10,%11,%12,%13,%14,%15,%16,%17,%18,%19,%20,%21,%22,%23,%24,%25,%26,%27,%28,%29,%30,%31}"
#define D16 "{%0,%1,%2,%3,%4,%5,%6,%7,%8,%9,%10,%11,%12,%13,%14,%15}"
#define D8 "{%0,%1,%2,%3,%4,%5,%6,%7}"
template <int ACC> __device__ __forceinline__ void hmma_n128t(uint32_t (&d)[32], const uint32_t (&a)[4], uint64_t db) {
  if (ACC)
    asm volatile("wgmma.mma_async.sync.aligned.m64n128k16.f16.f16.f16 " D32 ", {%32,%33,%34,%35}, %36, 1, 1, 1, 1;\n"
                 : U32("+r", d, 0) : "r"(a[0]), "r"(a[1]), "r"(a[2]), "r"(a[3]), "l"(db));
  else
    asm volatile("wgmma.mma_async.sync.aligned.m64n128k16.f16.f16.f16 " D32 ", {%32,%33,%34,%35}, %36, 0, 1, 1, 1;\n"
                 : U32("=r", d, 0) : "r"(a[0]), "r"(a[1]), "r"(a[2]), "r"(a[3]), "l"(db));
}
template <int ACC, int TB> __device__ __forceinline__ void hmma_n32(uint32_t (&d)[8], const uint32_t (&a)[4], uint64_t db) {
  if (ACC)
    asm volatile("wgmma.mma_async.sync.aligned.m64n32k16.f16.f16.f16 " D8 ", {%8,%9,%10,%11}, %12, 1, 1, 1, %13;\n"
                 : U8("+r", d, 0) : "r"(a[0]), "r"(a[1]), "r"(a[2]), "r"(a[3]), "l"(db), "n"(TB));
  else
    asm volatile("wgmma.mma_async.sync.aligned.m64n32k16.f16.f16.f16 " D8 ", {%8,%9,%10,%11}, %12, 0, 1, 1, %13;\n"
                 : U8("=r", d, 0) : "r"(a[0]), "r"(a[1]), "r"(a[2]), "r"(a[3]), "l"(db), "n"(TB));
}
template <int ACC> __device__ __forceinline__ void hmma_n64t(uint32_t (&d)[16], const uint32_t (&a)[4], uint64_t db) {
  if (ACC)
    asm volatile("wgmma.mma_async.sync.aligned.m64n64k16.f16.f16.f16 " D16 ", {%16,%17,%18,%19}, %20, 1, 1, 1, 1;\n"
                 : U16("+r", d, 0) : "r"(a[0]), "r"(a[1]), "r"(a[2]), "r"(a[3]), "l"(db));
  else
    asm volatile("wgmma.mma_async.sync.aligned.m64n64k16.f16.f16.f16 " D16 ", {%16,%17,%18,%19}, %20, 0, 1, 1, 1;\n"
                 : U16("=r", d, 0) : "r"(a[0]), "r"(a[1]), "r"(a[2]), "r"(a[3]), "l"(db));
}
template <int N> __device__ __forceinline__ void fence_regs(uint32_t (&d)[N]) {
#pragma unroll
  for (int i = 0; i < N; i++) asm volatile("" : "+r"(d[i])::"memory");
}
__device__ __forceinline__ uint32_t hmul(uint32_t a, uint32_t b) { uint32_t r; asm("mul.rn.f16x2 %0, %1, %2;\n" : "=r"(r) : "r"(a), "r"(b)); return r; }
__device__ __forceinline__ uint32_t hadd(uint32_t a, uint32_t b) { uint32_t r; asm("add.rn.f16x2 %0, %1, %2;\n" : "=r"(r) : "r"(a), "r"(b)); return r; }
__device__ __forceinline__ uint32_t hsub(uint32_t a, uint32_t b) { uint32_t r; asm("sub.rn.f16x2 %0, %1, %2;\n" : "=r"(r) : "r"(a), "r"(b)); return r; }
__device__ __forceinline__ uint32_t hfma(uint32_t a, uint32_t b, uint32_t c) { uint32_t r; asm("fma.rn.f16x2 %0, %1, %2, %3;\n" : "=r"(r) : "r"(a), "r"(b), "r"(c)); return r; }
__device__ __forceinline__ uint32_t hfnma(uint32_t a, uint32_t b, uint32_t c) {
  uint32_t r;
  asm("{\n.reg .b32 t;\nneg.f16x2 t, %1;\nfma.rn.f16x2 %0, t, %2, %3;\n}\n" : "=r"(r) : "r"(a), "r"(b), "r"(c));
  return r;
}
__device__ __forceinline__ uint32_t hrefl(uint32_t p, uint32_t s) {
  uint32_t r;
  asm("{\n.reg .b32 t;\nneg.f16x2 t, %2;\nfma.rn.f16x2 %0, %1, %3, t;\n}\n" : "=r"(r) : "r"(p), "r"(s), "r"(0x40004000u));
  return r;
}
__device__ __forceinline__ void bfly(uint32_t xr, uint32_t xi, uint32_t tr, uint32_t ti, uint32_t yr, uint32_t yi, uint32_t ur,
                                     uint32_t ui, uint32_t& sr, uint32_t& si, uint32_t& dr, uint32_t& di) {
  const uint32_t pr = hfnma(xi, ti, hmul(xr, tr)), pi = hfma(xi, tr, hmul(xr, ti));
  sr = hfnma(yi, ui, hfma(yr, ur, pr));
  si = hfma(yi, ur, hfma(yr, ui, pi));
  dr = hrefl(pr, sr);
  di = hrefl(pi, si);
}
template <int BH> __device__ __forceinline__ void fft_e1(const uint32_t (&d)[32], const uint32_t (&tw)[16], uint32_t (&a2)[2][2][4]) {
#pragma unroll
  for (int be = 0; be < 2; be++)
#pragma unroll
    for (int s = 0; s < 2; s++) {
      const int o = 16 * s + 8 * be + 2 * BH, p = 2 * BH;
      bfly(d[o], d[o + 1], tw[p], tw[p + 1], d[o + 4], d[o + 5], tw[p + 4], tw[p + 5], a2[be][0][s], a2[be][0][2 + s],
           a2[be][1][s], a2[be][1][2 + s]);
    }
}
__device__ __forceinline__ uint32_t hfms(uint32_t a, uint32_t b, uint32_t c) {
  uint32_t r;
  asm("{\n.reg .b32 t;\nneg.f16x2 t, %3;\nfma.rn.f16x2 %0, %1, %2, t;\n}\n" : "=r"(r) : "r"(a), "r"(b), "r"(c));
  return r;
}
template <int C, int J> __device__ __forceinline__ void fft_e2(const uint32_t (&d0)[8], const uint32_t (&d1)[8], uint32_t (&a3)[2][4]) {
  const uint32_t ur = d0[2 * J], ui = d0[4 + 2 * J], hr = d0[2 * J + 1], hi = d0[5 + 2 * J];
  const uint32_t vr = d1[2 * J], vi = d1[4 + 2 * J], gr = d1[2 * J + 1], gi = d1[5 + 2 * J];
  const uint32_t pr = hfnma(ui, hi, hmul(ur, hr)), pi = hfma(ui, hr, hmul(ur, hi));
  a3[0][2 + C] = pr;
  a3[0][C] = pi;
  a3[1][2 + C] = hfnma(vi, hi, hfma(vr, hr, hfnma(ui, gi, hfms(ur, gr, pi))));
  a3[1][C] = hfma(vi, hr, hfma(vr, hi, hfma(ui, gr, hfma(ur, gi, pr))));
}
__device__ __forceinline__ void fft_e3(const uint32_t (&d)[2][8], const uint32_t (&tw)[16], uint32_t zaddr) {
#pragma unroll
  for (int rho = 0; rho < 2; rho++) {
    uint32_t zr[4], zi[4];
#pragma unroll
    for (int nb = 0; nb < 4; nb++) {
      const uint32_t xi = d[nb >> 1][2 * (nb & 1) + rho], xr = d[nb >> 1][4 + 2 * (nb & 1) + rho];
      const uint32_t tr = tw[8 + 4 * rho + 2 * (nb & 1)], ti = tw[9 + 4 * rho + 2 * (nb & 1)];
      zr[nb] = hfnma(xi, ti, hmul(xr, tr));
      zi[nb] = hfma(xi, tr, hmul(xr, ti));
    }
    stsm4(zaddr + rho * 2048, zr[0], zr[1], zr[2], zr[3]);
    stsm4(zaddr + rho * 2048 + 1024, zi[0], zi[1], zi[2], zi[3]);
  }
}
__device__ __forceinline__ float bf_lo(uint32_t v) {
  uint32_t r;
  asm("prmt.b32 %0, %1, 0, 0x1044;\n" : "=r"(r) : "r"(v));
  return __uint_as_float(r);
}
__device__ __forceinline__ float bf_hi(uint32_t v) { return __uint_as_float(v & 0xffff0000u); }
__device__ __forceinline__ float ex2(float x) {
  float r;
  asm("ex2.approx.ftz.f32 %0, %1;\n" : "=f"(r) : "f"(x));
  return r;
}
__device__ __forceinline__ float rcp(float x) {
  float r;
  asm("rcp.approx.ftz.f32 %0, %1;\n" : "=f"(r) : "f"(x));
  return r;
}

__device__ __forceinline__ int g2_a(int s) { return ((0xA1054 >> (4 * s)) & 15) * 16384; }
__device__ __forceinline__ int g2_b(int s) { return ((0xCDB32 >> (4 * s)) & 15) * 16384; }
static_assert(OFF_U == 10 * 16384 && OFF_H == 12 * 16384 && OFF_OP == 4 * 16384, "units");
__device__ __forceinline__ int g2_k(int hp, int i) {
  return i < 2 ? hp ^ 1 ^ i : i < 4 ? (hp & ~1) ^ i : ((hp & ~3) + i) & 15; }
__device__ __forceinline__ int y_slot(int wg, int it) {
  static_assert(T_B2 == T_TW + 8192 && T_A1 == T_B2 + 4096, "y slots");
  return OFF_T + T_TW + ((it + 3) & 3) * 4096 + wg * 2048;
}

__device__ __forceinline__ void to_arr(uint32_t (&d)[4], uint4 v) { d[0] = v.x; d[1] = v.y; d[2] = v.z; d[3] = v.w; }

__device__ __forceinline__ void attn_stage(uint32_t sb, int blk, int lane, const float (&acc)[96], uint32_t (&k1)[2][4]) {
  const int lr = lane & 7, lm = lane >> 3;
  const uint32_t base = sb + OFF_VP + (blk * 16 + lr + 8 * (lm & 1)) * 128;
#pragma unroll
  for (int i = 0; i < 8; i++) k1[i >> 2][i & 3] = pack_bf16(acc[34 + 4 * i], acc[35 + 4 * i]);
  const uint32_t kh = sb + OFF_KH + blk * 2048 + lane * 16;
  sts128(kh, k1[0][0], k1[0][1], k1[0][2], k1[0][3]);
  sts128(kh + 512, k1[1][0], k1[1][1], k1[1][2], k1[1][3]);
#pragma unroll
  for (int j = 0; j < 8; j += 2)
    stsm4(base + (((j + (lm >> 1)) ^ lr) << 4), pack_bf16(acc[64 + 4 * j], acc[65 + 4 * j]),
          pack_bf16(acc[66 + 4 * j], acc[67 + 4 * j]), pack_bf16(acc[68 + 4 * j], acc[69 + 4 * j]),
          pack_bf16(acc[70 + 4 * j], acc[71 + 4 * j]));
}
__device__ __forceinline__ void attn_pack(const float (&acc)[96], uint32_t (&qa)[2][8], uint32_t (&k0)[2][4]) {
#pragma unroll
  for (int hd = 0; hd < 2; hd++) {
#pragma unroll
    for (int i = 0; i < 8; i++) {
      asm volatile("cvt.rn.bf16x2.f32 %0, %1, %2;\n" : "=r"(qa[hd][i]) : "f"(acc[16 * hd + 2 * i + 1]), "f"(acc[16 * hd + 2 * i]));
    }
#pragma unroll
    for (int i = 0; i < 4; i++) {
      asm volatile("cvt.rn.bf16x2.f32 %0, %1, %2;\n" : "=r"(k0[hd][i]) : "f"(acc[33 + 16 * hd + 4 * i]), "f"(acc[32 + 16 * hd + 4 * i]));
    }
  }
}
__device__ __forceinline__ void attn_own(const uint32_t (&k0)[2][4], const uint32_t (&k1)[2][4], bool le0, bool le1,
                                         const uint32_t (&qa)[2][8], float (&l)[2][4]) {
#pragma unroll
  for (int hd = 0; hd < 2; hd++) {
    float s0[4], s1[4];
    mma16816_z(s0, qa[hd][0], qa[hd][1], qa[hd][2], qa[hd][3], k0[hd][0], k0[hd][1]);
    mma16816_z(s1, qa[hd][0], qa[hd][1], qa[hd][2], qa[hd][3], k1[hd][0], k1[hd][1]);
    mma16816(s0, qa[hd][4], qa[hd][5], qa[hd][6], qa[hd][7], k0[hd][2], k0[hd][3]);
    mma16816(s1, qa[hd][4], qa[hd][5], qa[hd][6], qa[hd][7], k1[hd][2], k1[hd][3]);
    l[hd][0] = s0[0];
    l[hd][1] = s0[1];
    l[hd][2] = le0 ? s1[2] : s0[2];
    l[hd][3] = le1 ? s1[3] : s0[3];
  }
}
template <int N> __device__ __forceinline__ void quad_softmax(float (&x)[N][2], uint32_t (&pp)[N]) {
  const float c2 = 1.4426950408889634f;
  uint32_t q[N], mx[N / 2];
#pragma unroll
  for (int n = 0; n < N; n++) {
    const uint32_t r = pack_bf16(x[n][0], x[n][1]);
    q[n] = bfma2(r, 0x3e353e35u, bmul2(r, 0x379e379eu));
    x[n][0] = bf_lo(q[n]);
    x[n][1] = bf_hi(q[n]);
  }
#pragma unroll
  for (int n = 0; n < N / 2; n++)
    mx[n] = bmax2(__byte_perm(q[2 * n], q[2 * n + 1], 0x5410), __byte_perm(q[2 * n], q[2 * n + 1], 0x7632));
#pragma unroll
  for (int o = 1; o <= 2; o++)
#pragma unroll
    for (int n = 0; n < N / 2; n++) mx[n] = bmax2(mx[n], __shfl_xor_sync(0xffffffffu, mx[n], o));
  float m[N], t[N];
#pragma unroll
  for (int n = 0; n < N / 2; n++) {
    m[2 * n] = bf_lo(mx[n]);
    m[2 * n + 1] = bf_hi(mx[n]);
  }
#pragma unroll
  for (int n = 0; n < N; n++) {
    const float nm = -m[n] * c2;
    x[n][0] = ex2(fmaf(x[n][0], c2, nm));
    x[n][1] = ex2(fmaf(x[n][1], c2, nm));
    t[n] = x[n][0] + x[n][1];
  }
#pragma unroll
  for (int o = 1; o <= 2; o++)
#pragma unroll
    for (int n = 0; n < N; n++) t[n] += __shfl_xor_sync(0xffffffffu, t[n], o);
#pragma unroll
  for (int n = 0; n < N; n++) {
    const float inv = rcp(t[n]);
    pp[n] = pack_bf16(x[n][0] * inv, x[n][1] * inv);
  }
}
__device__ __forceinline__ void attn_pv(uint32_t dst, const uint32_t (&va)[4], const uint32_t (&vb)[4], uint32_t pp,
                                        uint32_t maskLE) {
  const uint32_t b0 = pp & ~maskLE, b1 = pp & maskLE;
  float oa[4], ob[4];
  mma16816_z(oa, va[0], va[1], va[2], va[3], b0, b1);
  mma16816_z(ob, vb[0], vb[1], vb[2], vb[3], b0, b1);
  stsm4t(dst, pack_bf16(oa[0], oa[1]), pack_bf16(oa[2], oa[3]), pack_bf16(ob[0], ob[1]), pack_bf16(ob[2], ob[3]));
}

template <int MODE>
__global__ void __cluster_dims__(2, 1, 1) __launch_bounds__(NTHREADS, 1)
fused_kernel(const Params p, const __grid_constant__ CUtensorMap tmX, const __grid_constant__ CUtensorMap tmW,
             const __grid_constant__ CUtensorMap tmWo,
             const __grid_constant__ CUtensorMap tmQ,
             const __grid_constant__ CUtensorMap tmXh, const __grid_constant__ CUtensorMap tmWh) {
  extern __shared__ __align__(1024) uint8_t smem[];
  const uint32_t sb = smem_u32(smem) - OFF_L0;
  const uint32_t bars = sb + OFF_BAR;
  const int tid = threadIdx.x, lane = tid & 31, warp = __shfl_sync(0xffffffffu, tid >> 5, 0);
  const int rank = blockIdx.x & 1;
  const bool halo_cta = blockIdx.x < 4;
  if (halo_cta && MODE != 0) return;
  int grp, mem;
  {
    const int t = (blockIdx.x >> 1) - 4, u = t - 32;
    const int q7 = (u * 37) >> 8;
    const bool lo = (unsigned)t < 32u, mid = (unsigned)u < 28u;
    grp = lo ? (t & 7) : (mid ? 1 + u - 7 * q7 : 0);
    mem = lo ? (t >> 3) : (mid ? 4 + q7 : (t < 0 ? t + 6 : t - 54));
  }
  const int rg = (grp >> 2) * 4 + (mem >> 1), hp = (grp & 3) * 4 + (mem & 1) * 2 + rank;
  const int rb2 = (grp >> 2) * 8 + mem, cb2 = (grp & 3) * 2 + rank;
  const int chb = grp * 16 + mem * 2 + rank;
  const int cta = rg * 16 + hp;
  const int par = rg >> 2, gidx = rg & 3;

  if (tid < 256 && !halo_cta && MODE != 2) {
    const int r = tid >> 3, c = tid & 7;
    const uint32_t so = r * 128 + ((c ^ (r & 7)) << 4);
    const __nv_bfloat16* wg0 = p.w + (size_t)r * (3 * DM) + hp * 64 + c * 8;
    const __nv_bfloat16* xg0 = p.x + (size_t)(2 * (gidx * 256 + r) + par) * DM + c * 8;
#pragma unroll
    for (int j = 0; j < 3; j++) cp_async16n(sb + OFF_1B + j * 4096 + so, wg0 + j * DM);
#pragma unroll
    for (int i = 0; i < 8; i++) cp_async16n(sb + i * 4096 + so, xg0 + (size_t)i * 64 * DM);
    asm volatile("cp.async.commit_group;\n" ::: "memory");
  }
  if (tid == 256) {
    prefetch_tmap(halo_cta ? &tmXh : &tmX);
#pragma unroll
    for (int i = 0; i < NS1B; i++) mbar_init(bars + 8 * (BAR_FULLB + i), 1);
#pragma unroll
    for (int i = 0; i < NS1A; i++) mbar_init(bars + 8 * (BAR_FULLA + i), 1);
    asm volatile("fence.mbarrier_init.release.cluster;\n" ::: "memory");
    if (!halo_cta && MODE != 2) {
      mbar_expect_tx(bars + 8 * (BAR_FULLB + 1), STG1B);
      tma_load_3d(sb + OFF_1B + 1 * STG1B, &tmW, bars + 8 * (BAR_FULLB + 1), hp * 64, 32, 0);
      mbar_expect_tx(bars + 8 * (BAR_FULLB + 2), STG1B);
      tma_load_3d(sb + OFF_1B + 2 * STG1B, &tmW, bars + 8 * (BAR_FULLB + 2), hp * 64, 64, 0);
    } else {
      prefetch_tmap(&tmWh);
    }
  } else if (tid == 288) {
#pragma unroll
    for (int i = 0; i < NS1A; i++) mbar_init(bars + 8 * (BAR_EMPTYA + i), 4);
#pragma unroll
    for (int i = 0; i < NS1B; i++) mbar_init(bars + 8 * (BAR_EMPTYB + i), 2);
    asm volatile("fence.mbarrier_init.release.cluster;\n" ::: "memory");
  } else if (tid == 320) {
#pragma unroll
    for (int i = 0; i < NS2; i++) {
      mbar_init(bars + 8 * (BAR_FULL2 + i), 1);
      mbar_init(bars + 8 * (BAR_EMPTY2 + i), 4);
    }
    mbar_init(bars + 8 * BAR_DEAD, 2);
    mbar_init(bars + 8 * (BAR_DEAD + 1), 2);
    mbar_init(bars + 8 * BAR_X, 2);
    mbar_init(bars + 8 * BAR_REL, 2);
    asm volatile("fence.mbarrier_init.release.cluster;\n" ::: "memory");
  } else if (tid == 352) {
    mbar_init(bars + 8 * BAR_T, 1);
    mbar_init(bars + 8 * BAR_UH, 3);
    mbar_init(bars + 8 * BAR_LFREE, 4);
    mbar_init(bars + 8 * BAR_LAND, 1);
    mbar_init(bars + 8 * BAR_U, 1);
    mbar_init(bars + 8 * BAR_Q, 1);
    mbar_init(bars + 8 * BAR_STG, 9);
    asm volatile("fence.mbarrier_init.release.cluster;\n" ::: "memory");
  }
  if (warp == 8) PROF2(23);
  cluster_sync_all();
  if (warp == 8) PROF2(24);

  if (warp >= 8) {
    const int hw = warp - 8;
    const int lr = lane & 7, lm = lane >> 3;
    auto g1_issue_a = [&](int j, int s) {
      const uint32_t fb = bars + 8 * (BAR_FULLA + s);
      mbar_expect_tx(fb, STG1A);
      tma_load_3d_mc(sb + s * STG1A + rank * 16384, &tmX, fb, j * 64, par, gidx * 256 + rank * 128);
    };
    auto g1_issue_b = [&](int kb, int s) {
      const uint32_t fb = bars + 8 * (BAR_FULLB + s);
      mbar_expect_tx(fb, STG1B);
      tma_load_3d(sb + OFF_1B + s * STG1B, &tmW, fb, hp * 64, kb * 32, 0);
    };
    asm volatile("setmaxnreg.dec.sync.aligned.u32 %0;\n" :: "n"(REG_HELP));

    if (halo_cta) {
      if (hw == 0) {
        int s = 0, ph = 1;
#pragma unroll 1
        for (int kb = 0; kb < 16; kb++) {
          mbar_wait(bars + 8 * (BAR_EMPTYB + s), ph);
          const uint32_t fb = bars + 8 * (BAR_FULLB + s), st = sb + s * STGH;
          if (elect_one()) {
            mbar_expect_tx(fb, STGH);
            tma_load_4d(st, &tmXh, fb, kb * 64, 248, 0, 0);
            tma_load_3d(st + 8192, &tmWh, fb, 0, kb * 64, 16 + blockIdx.x * 4);
            tma_load_3d(st + 8192 + 32768, &tmWh, fb, 0, kb * 64, 32 + blockIdx.x * 4);
          }
          if (++s == 3) { s = 0; ph ^= 1; }
        }
      }
      __syncwarp();
    } else if (hw == 0) {
      uint32_t epoch = 0;
      if (lane < (MODE == 2 ? NS2 : 2)) mbar_arrive_cluster_n(mapa(bars, rank) + 8 * (BAR_EMPTY2 + lane), 4);
      if (MODE != 2) {
      epoch = ld_relaxed(g_flag_o + 2 * cta) + 1;
      if (lane == 0) {
        mbar_expect_tx(bars + 8 * BAR_U, 32768);
        mbar_expect_tx(bars + 8 * BAR_LAND, 32768 + 64);
        mbar_expect_tx(bars + 8 * BAR_Q, 32768);
        mbar_expect_tx(bars + 8 * BAR_T, T_END);
      }
      {
        int sa = 1, pha = 1, sbb = 2, phb = 1;
#pragma unroll 1
        for (int kb = 2; kb < 32; kb++) {
          if (!(kb & 1)) {
            mbar_wait(bars + 8 * (BAR_EMPTYA + sa), pha);
            if (elect_one()) g1_issue_a(kb >> 1, sa);
            if (++sa == NS1A) { sa = 0; pha ^= 1; }
          }
          mbar_wait(bars + 8 * (BAR_EMPTYB + sbb), phb);
          if (kb > 2 && elect_one()) g1_issue_b(kb, sbb);
          __syncwarp();
          if (kb >= PF0 && kb < PF0 + 12)
            prefetch_l2((kb < PF0 + 8 ? p.q + (size_t)chb * 16384 + (kb - PF0) * 2048 : p.wo + (size_t)chb * 8192 + (kb - PF0 - 8) * 2048) + lane * 64);
          if (kb == 4) PROF2(27);
          if (kb == 1) PROF2(38);
          if (kb == 2) PROF2(39);
          if (++sbb == NS1B) { sbb = 0; phb ^= 1; }
        }
      }
      static_assert(32 % NS1B == 2 && (32 / NS1B) % 2 == 0 && OFF_Q == OFF_1B && 2 * STG1B == 6 * 4096, "slots / parity of these loads");
      const uint8_t* tab = reinterpret_cast<const uint8_t*>(g_tab);
      if (lane == 0) {
        prefetch_tmap(&tmWo);
        prefetch_tmap(&tmQ);
        bulk_load(sb + OFF_T + T_A1, tab + T_A1, T_END - T_A1, bars + 8 * BAR_T);
        mbar_wait(bars + 8 * (BAR_EMPTYB + 2), 1);
        tma_load_5d(sb + OFF_Q + 6 * 4096, &tmQ, bars + 8 * BAR_Q, (chb & ~1) * 8, rank * 32 + 24);
        tma_load_5d(sb + OFF_Q + 7 * 4096, &tmQ, bars + 8 * BAR_Q, (chb & ~1) * 8, rank * 32 + 28);
        if (gidx != 0) wait_flag(g_flag_h + (hp >> 2), epoch);
      }
      __syncwarp();
      {
        uint4 hk0 = make_uint4(0, 0, 0, 0), hk1 = hk0, hv0 = hk0, hv1 = hk0;
        if (gidx != 0) {
          const uint4* src = g_halo + cta * 128 + lane;
          hk0 = __ldcg(src); hk1 = __ldcg(src + 32); hv0 = __ldcg(src + 64); hv1 = __ldcg(src + 96);
        }
        if (lane == 0) {
          mbar_wait(bars + 8 * (BAR_EMPTYB + 3), 1);
          bulk_load(sb + OFF_T, tab, T_TW, bars + 8 * BAR_T);
        }
        __syncwarp();
        PROF2(18);
        sts128(sb + OFF_L0 + lane * 16, hk0.x, hk0.y, hk0.z, hk0.w);
        sts128(sb + OFF_L0 + 512 + lane * 16, hk1.x, hk1.y, hk1.z, hk1.w);
        stsm4(sb + OFF_L0 + 1024 + lr * 128 + ((lm ^ lr) << 4), hv0.x, hv0.y, hv0.z, hv0.w);
        stsm4(sb + OFF_L0 + 1024 + lr * 128 + (((4 + lm) ^ lr) << 4), hv1.x, hv1.y, hv1.z, hv1.w);
        __syncwarp();
        if (lane == 0) {
          mbar_arrive(bars + 8 * BAR_STG);
          mbar_wait(bars + 8 * (BAR_EMPTYB + 4), 1);
          bulk_load(sb + OFF_T + T_TW, tab + T_TW, T_A1 - T_TW, bars + 8 * BAR_T);
          mbar_wait(bars + 8 * BAR_EMPTYB, 0);
#pragma unroll 1
          for (int i = 0; i < 6; i++) tma_load_5d(sb + OFF_Q + i * 4096, &tmQ, bars + 8 * BAR_Q, (chb & ~1) * 8, rank * 32 + i * 4);
        }
        __syncwarp();
      }
      }
      if (MODE != 1) {
        auto korder = [&](int i) { return MODE == 2 ? i : g2_k(hp, i); };
        const __nv_bfloat16* osrc = g_o + (size_t)(rb2 >> 1) * 16 * 16384 + ((rb2 & 1) * 2 + rank) * 4096;
        const uint32_t* flag = g_flag_o + ((rb2 >> 1) * 32 + korder(lane & 15) * 2 + (rb2 & 1));
        uint32_t ready = MODE == 0 ? 0u : ~0u, pv = 0;
        auto look = [&]() {
          ready |= __ballot_sync(0xffffffffu, pv == epoch);
          asm volatile("fence.acquire.gpu;\n" ::: "memory");
          fence_async_all();
        };
        const __nv_bfloat16* o23[2] = {osrc + korder(2) * 16384, osrc + korder(3) * 16384};
        if (MODE == 0) {
          asm volatile("" : "+l"(o23[0]), "+l"(o23[1]), "+l"(flag));
          if (lane < 4 && lane != 1) mbar_expect_tx(bars + 8 * (BAR_FULL2 + lane), STG2);
          mbar_wait_idle(bars + 8 * (BAR_EMPTY2 + 2), 0);
          mbar_wait(bars + 8 * (BAR_EMPTY2 + 3), 0);
          mbar_wait_idle(bars + 8 * BAR_REL, 0);
          if (elect_one()) {
            tma_load_3d(sb + g2_b(0), &tmWo, bars + 8 * BAR_FULL2, 0, korder(0) * 64, cb2 * 2);
            tma_load_3d(sb + g2_b(1), &tmWo, bars + 8 * (BAR_FULL2 + 1), 0, korder(1) * 64, cb2 * 2);
          }
        }
#pragma unroll
        for (int i = MODE == 0 ? 2 : 0; i < 16; i++) {
          const int kb = korder(i), s = i % NS2, ph = (i / NS2) & 1;
          const uint32_t fb = bars + 8 * (BAR_FULL2 + s);
          if (!((ready >> i) & 1)) {
            int n = 0;
            do {
              ready |= __ballot_sync(0xffffffffu, ld_acquire(flag) == epoch);
            } while (!((ready >> i) & 1) && ++n < SPIN_LIMIT);
            fence_async_all();
          }
          if (i == 2) PROF(21);
          const bool pre = MODE == 0 && i < 4;
          if (!pre) mbar_wait(bars + 8 * (BAR_EMPTY2 + s), ph);
          if (elect_one()) {
            if (!pre) mbar_expect_tx(fb, STG2);
            asm volatile(
                "cp.async.bulk.shared::cluster.global.mbarrier::complete_tx::bytes.multicast::cluster [%0], [%1], %2, [%3], %4;\n"
                ::"r"(sb + g2_a(s) + rank * 8192), "l"(pre ? o23[i & 1] : osrc + kb * 16384), "r"(8192), "r"(fb), "h"((uint16_t)3) : "memory");
            if (!pre) tma_load_3d(sb + g2_b(s), &tmWo, fb, 0, kb * 64, cb2 * 2);
          }
          if (MODE == 0 && i == LA0) pv = ld_relaxed(flag);
          if (MODE == 0 && i == LA1) look();
          if (i == 3) PROF(37);

        }
      }
      __syncwarp();
    } else if (MODE != 2) {
      {
        const int g = lane >> 2, t = lane & 3;
        uint32_t w[2][4];
#pragma unroll
        for (int h = 0; h < 2; h++) {
          const uint2 x = __ldg(reinterpret_cast<const uint2*>(p.shift_k + ((chb & ~1) * 8 + h * 8 + g) * 4));
          w[h][0] = __byte_perm(x.x, x.x, 0x1010);
          w[h][1] = __byte_perm(x.x, x.x, 0x3232);
          w[h][2] = __byte_perm(x.y, x.y, 0x1010);
          w[h][3] = __byte_perm(x.y, x.y, 0x3232);
        }
        auto swz = [](int r) { return (((r & 29) | ((r ^ (r >> 2)) & 2)) << 5) | (r & 16); };
        const uint32_t kring = sb + OFF_H + (hw - 1) * 8192, vring = kring + 4096;
        const int s0 = rank * 32 + (hw - 1) * 11, s1 = hw == 3 ? rank * 32 + 32 : s0 + 11;
        const size_t goff = (size_t)(lane >> 1) * DM + (chb & ~1) * 8 + (lane & 1) * 8;
        const __nv_bfloat16* kg = p.k + goff;
        const __nv_bfloat16* vg = p.v + goff;
        const uint32_t d0 = swz(lane >> 1) ^ ((lane & 1) << 4), d1 = swz(16 + (lane >> 1)) ^ ((lane & 1) << 4);
        auto issue = [&](int st) {
          const uint32_t so = (st & 3) << 10;
          cp_async16(kring + so + d0, kg + (size_t)st * 32 * DM, 16);
          cp_async16(kring + so + d1, kg + (size_t)(st * 32 + 16) * DM, 16);
          cp_async16(vring + so + d0, vg + (size_t)st * 32 * DM, 16);
          cp_async16(vring + so + d1, vg + (size_t)(st * 32 + 16) * DM, 16);
        };
        const int xa = 8 * (lr >> 1) + 2 * lm + (lr & 1), xb = 8 * (lr >> 1) - 4 + 2 * (lm & 1) + (lr & 1);
        const uint32_t la = swz(xa), lb = swz(xb & 31);
        const int backb = xb < 0 ? 1 : 0;
        const uint32_t ud[2] = {mapa(sb + OFF_U + g * 4096 + t * 16, 0), mapa(sb + OFF_U + g * 4096 + t * 16, 1)};
        const uint32_t ub[2] = {mapa(bars + 8 * BAR_U, 0), mapa(bars + 8 * BAR_U, 1)};
        if (lane == 0) mbar_wait(bars + 8 * (BAR_FULLB + NS1B - 1), 0);
        __syncwarp();
        if (lane >= 24) cp_async16(kring + (((s0 - 1) & 3) << 10) + d1, s0 > 0 ? kg + (size_t)(s0 * 32 - 16) * DM : kg, s0 > 0 ? 16 : 0);
        issue(s0);
        asm volatile("cp.async.commit_group;\n" ::: "memory");
        issue(s0 + 1);
        asm volatile("cp.async.commit_group;\n" ::: "memory");
#pragma unroll 1
        for (int st = s0; st < s1; st++) {
          if (st + 2 < s1) issue(st + 2);
          if (hw == 1 && st - s0 < 8) prefetch_l2(p.ssm_k + (size_t)(chb * 8 + st - s0) * SEQ + lane * 64);
          if (hw == 2 && st == s0 + 4 && lane < 2) prefetch_l2(g_tab + (chb * 2 + lane) * 32);
          const uint32_t uo = (st ^ ((g ^ (st >> 2)) & 1)) * 64;
          asm volatile("cp.async.commit_group;\n" ::: "memory");
          asm volatile("cp.async.wait_group 2;\n" ::: "memory");
          __syncwarp();
#pragma unroll
          for (int h = 0; h < 2; h++) {
            uint32_t e[6], vv[4], e4[4];
            ldsm4t(e4, kring + ((st & 3) << 10) + (la ^ (h << 4)));
            ldsm2t(e[0], e[1], kring + (((st - backb) & 3) << 10) + (lb ^ (h << 4)));
            ldsm4t(vv, vring + ((st & 3) << 10) + (la ^ (h << 4)));
            e[2] = e4[0]; e[3] = e4[1]; e[4] = e4[2]; e[5] = e4[3];
            uint32_t o[5];
#pragma unroll
            for (int i = 0; i < 5; i++) o[i] = __byte_perm(e[i], e[i + 1], 0x5432);
#pragma unroll
            for (int i = 0; i < 4; i++) {
              uint32_t a = bmul2(o[i], w[h][3]);
              a = bfma2(e[i + 1], w[h][2], a);
              a = bfma2(o[i + 1], w[h][1], a);
              a = bfma2(e[i + 2], w[h][0], a);
              vv[i] = bmul2(a, vv[i]);
            }
            st_async128(ud[h] + uo, ub[h], vv[0], vv[1], vv[2], vv[3]);
          }
          __syncwarp();
        }
        PROF(16);
      }
      {
        const int rw = (lane >> 3) + (lane & 4), ck = lane & 3;
        const uint32_t so = rw * 64 + ck * 16, dof = rw * 128 + ((ck ^ rw) << 4);
        const uint8_t* hsrc = reinterpret_cast<const uint8_t*>(p.ssm_k + (size_t)chb * 8 * SEQ) + so;
        const float dv = lane < 8 ? __bfloat162float(p.ssm_D[chb * 8 + lane]) : 0.f;
        uint32_t x[32];
        auto load = [&](const uint8_t* src, int i) {
          asm volatile("ld.v4.u32 {%0,%1,%2,%3}, [%4];\n" : "=r"(x[4 * i]), "=r"(x[4 * i + 1]), "=r"(x[4 * i + 2]), "=r"(x[4 * i + 3])
                       : "l"(src + i * 512) : "memory");
        };
#pragma unroll
        for (int i = 0; i < 8; i++) load(hsrc + (hw - 1) * 4096, i);
        nb_sync(NB_HELP3, 96);
        mbar_wait(bars + 8 * BAR_U, 0);
        int eh = 0;
#pragma unroll 1
        for (int n = 2 * (hw - 1); n < 16; n += (n & 1) ? 5 : 1) {
          const int c = n >> 1;
          const uint8_t* nsrc = (n & 1) ? hsrc + (c < 5 ? c + 3 : c) * 4096
                                        : smem - OFF_L0 + OFF_U + c * 4096 + (so ^ (((c ^ (lane >> 2)) & 1) << 6));
          const uint32_t dst = sb + ((n & 1) ? OFF_U : OFF_H) + c * 4096 + dof;
          const float dc = __shfl_sync(0xffffffffu, dv, c);
          const float h0 = bf_lo(x[0]) + ((lane | (n & 1)) == 0 ? dc : 0.f), h1 = bf_hi(x[0]);
          x[0] = pack_bf16(h0, h1);
          uint32_t m[2] = {x[0], x[1]};
#pragma unroll
          for (int i = 2; i < 32; i++) asm("max.xorsign.abs.bf16x2 %0, %0, %1;\n" : "+r"(m[i & 1]) : "r"(x[i]));
          asm("max.xorsign.abs.bf16x2 %0, %0, %1;\n" : "+r"(m[0]) : "r"(m[1]));
          const uint32_t e = max(__reduce_max_sync(0xffffffffu, max((m[0] >> 7) & 255u, (m[0] >> 23) & 255u)), 5u);
          const uint32_t sc = (259u - e) * 0x00800080u;
#pragma unroll
          for (int i = 0; i < 8; i++) {
            uint32_t o[4];
#pragma unroll
            for (int j = 0; j < 4; j++) {
              const uint32_t v = bmul2(x[4 * i + j], sc);
              asm("cvt.rn.f16x2.f32 %0, %1, %2;\n" : "=r"(o[j]) : "f"(bf_hi(v)), "f"(i + j == 0 ? h0 * bf_hi(sc) : bf_lo(v)));
            }
            sts128((dst + (i & 3) * 1024) ^ ((i >> 2) << 6), o[0], o[1], o[2], o[3]);
            load(nsrc, i);
          }
          if (n & 1) {
            const int f = min(max((int)e + eh - 129, 0), 254);
            if (lane < 2)
              asm volatile("st.async.weak.shared::cluster.mbarrier::complete_tx::bytes.b32 [%0], %2, [%1];\n"
                           ::"r"(mapa(sb + OFF_SC + rank * 32 + c * 4, lane)), "r"(mapa(bars + 8 * BAR_LAND, lane)), "r"(f << 7) : "memory");
          }
          eh = e;
        }
        fence_async_smem();
        __syncwarp();
        if (lane == 0) mbar_arrive(bars + 8 * BAR_UH);
        PROF(32);
      }
      if (hw < 3) {
        const uint32_t rb = mapa(bars, lane & 1);
        const uint32_t epoch = ld_relaxed(g_flag_o + (2 * cta + hw - 1)) + 1;
        const bool own = hw - 1 == (rb2 & 1);
        nb_sync(NB_OREADY + hw - 1, 160);
        if (lane == 0) {
          asm volatile("cp.async.bulk.global.shared::cta.bulk_group [%0], [%1], %2;\n" ::"l"(g_o + (size_t)cta * 16384 + (hw - 1) * 8192),
                       "r"(sb + OFF_OP + (own ? 16384 : 0)), "r"(16384) : "memory");
          bulk_commit();
        }
        if (lane < 2) {
          mbar_arrive_cluster(rb + 8 * (BAR_EMPTY2 + 2));
          mbar_arrive_cluster(rb + 8 * (BAR_EMPTY2 + 3));
        }
        if (lane == 0) {
          bulk_wait0();
          if (own) mbar_expect_tx(bars + 8 * (BAR_FULL2 + 1), 16384);
          mbar_arrive_cluster(mapa(bars, own ? rank : rank ^ 1) + 8 * BAR_X);
          st_release(g_flag_o + (2 * cta + hw - 1), epoch);
          mbar_arrive(bars + 8 * BAR_REL);
        }
        __syncwarp();
        PROF(own ? 17 : 19);
      } else {
        if (MODE == 0) {
          mbar_wait_idle(bars + 8 * BAR_X, 0);
          if (elect_one())
            asm volatile("cp.async.bulk.shared::cluster.shared::cta.mbarrier::complete_tx::bytes [%0], [%1], %2, [%3];\n"
                         ::"r"(mapa(sb + OFF_OP, rank ^ 1)), "r"(sb + OFF_OP + 16384), "r"(16384),
                         "r"(mapa(bars + 8 * BAR_FULL2, rank ^ 1)) : "memory");
        }
        if (MODE == 0) {
          mbar_wait_idle(bars + 8 * BAR_DEAD, 0);
          if (elect_one()) {
            tma_load_3d(sb + g2_b(2), &tmWo, bars + 8 * (BAR_FULL2 + 2), 0, g2_k(hp, 2) * 64, cb2 * 2);
            tma_load_3d(sb + g2_b(3), &tmWo, bars + 8 * (BAR_FULL2 + 3), 0, g2_k(hp, 3) * 64, cb2 * 2);
          }
        }
        __syncwarp();
      }
    }
    if (!halo_cta && MODE != 2 && (F4 || hw)) {
      {
        const int c8 = (4 * (lr >> 1) + 2 * (lm & 1) + (lr & 1)) & 7;
        const bool own = (lr >> 2) == rank;
        const uint32_t ya = sb + (own ? y_slot(c8 & 1, c8 >> 1) : OFF_LAND + c8 * 2048);
        const uint32_t yx = ((lm >> 1) ^ lr) << 4;
        const int row = (lane >> 4) * 8 + ((lane >> 3) & 1) * 16 + ((lane >> 2) & 1);
        uint2* og = reinterpret_cast<uint2*>(p.out + (size_t)(rank * 1024 + row) * (2 * DM) + (chb & ~1) * 8 + (lane & 3) * 4);
        const uint32_t qa = sb + OFF_Q + (lane >> 4) * 512 + (lane & 15) * 8;
        mbar_wait(bars + 8 * BAR_Q, 0);
        mbar_wait_idle(bars + 8 * BAR_LAND, 0);
        PROF(33);
        const uint32_t t0 = clock();
        const uint4 s4 = lds128(sb + OFF_SC + (lane & 3) * 16);
        const uint32_t sc[2] = {s4.x | (s4.y << 16), s4.z | (s4.w << 16)};
        auto fin = [&](uint32_t q2, uint32_t y2, uint32_t s2) {
          float lo, hi;
          asm("{\n.reg .b16 l, h;\nmov.b32 {l, h}, %2;\ncvt.f32.f16 %0, l;\ncvt.f32.f16 %1, h;\n}\n" : "=f"(lo), "=f"(hi) : "r"(y2));
          return bmul2(q2, bmul2(pack_bf16(lo, hi), s2));
        };
#pragma unroll 1
        for (int j = hw ? hw - 1 : 15; j < (hw ? 16 - F4 : 16); j += 3) {
          uint32_t y[4][4];
          uint2 q[8];
          while (hw && (uint32_t)clock() - t0 < j * PACE) __nanosleep(40);
          const uint32_t qj = qa + j * 2048;
#pragma unroll
          for (int i = 0; i < 4; i++) ldsm4t(y[i], ya + j * 128 + (yx ^ (i << 5)));
#pragma unroll
          for (int i = 0; i < 8; i++) q[i] = lds64(qj + (i >> 2) * 1024 + (i & 3) * 128);
#pragma unroll
          for (int i = 0; i < 8; i++) {
            og[(size_t)(j * 64 + (i >> 2) * 32 + (i & 3) * 2) * (2 * DM / 4)] =
                make_uint2(fin(q[i].x, y[i >> 1][2 * (i & 1)], sc[0]), fin(q[i].y, y[i >> 1][2 * (i & 1) + 1], sc[1]));
            if (i < 7) asm volatile("nanosleep.u32 %0;\n" ::"r"(FINE) : "memory");
          }
        }
      }
      PROF(22);
    }
    cluster_sync_all();
  } else {
    asm volatile("setmaxnreg.inc.sync.aligned.u32 %0;\n" :: "n"(REG_MATH));
    if (warp == 0) PROF2(26);
    const int wg = warp >> 2;
    const int wtid = tid & 127;
    const bool signaller = (wtid == 0) || (wtid == 32);
    const uint32_t rbars = mapa(bars, wtid >> 5 & 1);

    if (halo_cta) {
      const uint32_t epoch = ld_relaxed(g_flag_h + blockIdx.x) + 1;
      float acc0[64], acc1[64];
      int s = 0, ph = 0;
#pragma unroll 1
      for (int kb = 0; kb < 16; kb++) {
        mbar_wait(bars + 8 * (BAR_FULLB + s), ph);
        const uint32_t st = sb + s * STGH;
        const uint64_t da = mkdesc(st, 16, 1024, 1);
        const uint64_t db = mkdesc(st + 8192 + wg * 32768, 8192, 1024, 1);
        wg_fence();
#pragma unroll
        for (int kk = 0; kk < 4; kk++) {
          wgmma_n128(acc0, da + 2 * kk, db + 128 * kk, kb + kk);
          wgmma_n128(acc1, da + 2 * kk, db + 1024 + 128 * kk, kb + kk);
        }
        wg_commit();
        wg_wait<0>();
        if (wtid == 0) mbar_arrive(bars + 8 * (BAR_EMPTYB + s));
        if (++s == 3) { s = 0; ph ^= 1; }
      }
      fence_regs(acc0);
      fence_regs(acc1);
      if ((warp & 3) != 3) {
#pragma unroll
        for (int hh = 0; hh < 2; hh++) {
          uint4* dst = g_halo + ((hh * 4 + (warp & 3) + 1) * 16 + blockIdx.x * 4) * 128 + wg * 64 + lane;
#pragma unroll
          for (int j = 0; j < 4; j++) {
            const int o = 16 * j + 2 * hh;
            dst[(j >> 1) * 128 + (j & 1) * 32] =
                make_uint4(pack_bf16(acc0[o], acc0[o + 1]), pack_bf16(acc0[o + 4], acc0[o + 5]),
                           pack_bf16(acc0[o + 8], acc0[o + 9]), pack_bf16(acc0[o + 12], acc0[o + 13]));
            dst[(2 + (j >> 1)) * 128 + (j & 1) * 32] =
                make_uint4(pack_bf16(acc1[o], acc1[o + 1]), pack_bf16(acc1[o + 4], acc1[o + 5]),
                           pack_bf16(acc1[o + 8], acc1[o + 9]), pack_bf16(acc1[o + 12], acc1[o + 13]));
          }
        }
      }
      nb_sync(NB_G1DONE, 256);
      if (tid == 0) st_release(g_flag_h + blockIdx.x, epoch);
      PROF(36);
      cluster_sync_all();
      return;
    }

    float acc[64];
    auto g2_step = [&](int s, int kb) {
      const uint64_t da = mkdesc(sb + g2_a(s) + wg * 8192, 16, 1024, 1);
      const uint64_t db = mkdesc(sb + g2_b(s), 8192, 1024, 1);
      wg_fence();
      wgmma_n128(acc, da, db, kb);
      wgmma_n128(acc, da + 2, db + 128, 1);
      wgmma_n128(acc, da + 4, db + 256, 1);
      wgmma_n128(acc, da + 6, db + 384, 1);
      wg_commit();
    };

    if (MODE != 2) {
    uint32_t a1[2][4], tw[16], d1[32];
    const uint32_t tb = sb + OFF_T + wtid * 16;
    const uint64_t dx = mkdesc(sb + OFF_U + wg * 4096, OFF_H - OFF_U, 1024, 1);
    auto s1 = [&](int it) {
      hmma_n128t<0>(d1, a1[0], dx + it * 512);
      hmma_n128t<1>(d1, a1[1], dx + it * 512 + 128);
      wg_commit();
    };
    auto ldtw = [&](int i) {
      const uint4 v = lds128(tb + T_TW + i * 2048);
      tw[4 * i] = v.x; tw[4 * i + 1] = v.y; tw[4 * i + 2] = v.z; tw[4 * i + 3] = v.w;
    };
    {
      float acc0[96], acc1[96];
      int sa = 0, pha = 0, sbb = 0, phb = 0;
      asm volatile("cp.async.wait_group 0;\n" ::: "memory");
      fence_async_smem();
      nb_sync(NB_FIRST, 256);
      if (tid == 0) {
        mbar_arrive(bars + 8 * BAR_FULLA);
        mbar_arrive(bars + 8 * BAR_FULLB);
      }
      PROF(0 + wg);
#pragma unroll 1
      for (int kb = 0; kb < 30; kb++) {
        if (!(kb & 1)) mbar_wait(bars + 8 * (BAR_FULLA + sa), pha);
        mbar_wait(bars + 8 * (BAR_FULLB + sbb), phb);
        if (kb == 0) PROF2(0 + wg);
        if (kb == 4 && wg == 0) PROF2(28);
        if (kb == 8 && wg == 0) PROF2(29);
        if (kb == 16 && wg == 0) PROF2(30);
        const uint64_t da = mkdesc(sb + sa * STG1A + wg * 16384 + (kb & 1) * 64, 16, 1024, 1);
        const uint64_t db = mkdesc(sb + OFF_1B + sbb * STG1B, 4096, 1024, 1);
        wg_fence();
        wgmma_n192(acc0, da, db, kb);
        wgmma_n192(acc1, da + 512, db, kb);
        wgmma_n192(acc0, da + 2, db + 128, 1);
        wgmma_n192(acc1, da + 514, db + 128, 1);
        wg_commit();
        wg_wait<1>();
        if (kb > 0) {
          if (wtid == 64) mbar_arrive(bars + 8 * (BAR_EMPTYB + (sbb == 0 ? NS1B - 1 : sbb - 1)));
          if (!(kb & 1) && signaller) mbar_arrive_cluster(rbars + 8 * (BAR_EMPTYA + (sa == 0 ? NS1A - 1 : sa - 1)));
        }
        if (++sbb == NS1B) { sbb = 0; phb ^= 1; }
        if ((kb & 1) && ++sa == NS1A) { sa = 0; pha ^= 1; }
      }
      const int blk0 = wg * 8 + (warp & 3);
      const int lr = lane & 7, lm = lane >> 3;
      const bool le0 = 2 * (lane & 3) <= (lane >> 2), le1 = 2 * (lane & 3) + 1 <= (lane >> 2);
      const uint32_t maskLE = (le0 ? 0x0000FFFFu : 0u) | (le1 ? 0xFFFF0000u : 0u);
      uint32_t k0[2][2][4], k1[2][2][4], qa[2][2][8];
      float l[2][2][4];
      {
        static_assert(15 % NS1A == 0 && 30 % NS1B == 0, "slots of the last k blocks");
        mbar_wait(bars + 8 * BAR_FULLA, 1);
        mbar_wait(bars + 8 * BAR_FULLB, 0);
        mbar_wait(bars + 8 * (BAR_FULLB + 1), 0);
        const uint64_t da = mkdesc(sb + wg * 16384, 16, 1024, 1);
        const uint64_t db = mkdesc(sb + OFF_1B, 4096, 1024, 1);
        wg_fence();
#pragma unroll
        for (int i = 0; i < 4; i++) wgmma_n192(acc0, da + 2 * i, db + (i >> 1) * (STG1B >> 4) + (i & 1) * 128, 1);
        wg_commit();
        wg_wait<1>();
        if (wtid == 64) mbar_arrive(bars + 8 * (BAR_EMPTYB + NS1B - 1));
#pragma unroll
        for (int i = 0; i < 2; i++) wgmma_n192(acc1, da + 512 + 2 * i, db + (i >> 1) * (STG1B >> 4) + (i & 1) * 128, 1);
        wg_commit();
        wg_wait<1>();
        fence_regs(acc0);
        attn_stage(sb, blk0, lane, acc0, k1[0]);
#pragma unroll
        for (int i = 2; i < 4; i++) wgmma_n192(acc1, da + 512 + 2 * i, db + (i >> 1) * (STG1B >> 4) + (i & 1) * 128, 1);
        wg_commit();
        attn_pack(acc0, qa[0], k0[0]);
        wg_wait<0>();
        fence_regs(acc1);
      }
      if (wtid == 64) mbar_arrive(bars + 8 * BAR_EMPTYB);
      PROF(2 + wg);
      attn_stage(sb, blk0 + 4, lane, acc1, k1[1]);
      __syncwarp();
      if (lane == 0) mbar_arrive(bars + 8 * BAR_STG);
      mbar_wait(bars + 8 * BAR_U, 0);
      attn_pack(acc1, qa[1], k0[1]);
      attn_own(k0[0], k1[0], le0, le1, qa[0], l[0]);
      attn_own(k0[1], k1[1], le0, le1, qa[1], l[1]);
      static_assert(OFF_L0 + 2048 == OFF_VP, "halo V rows");
      const uint32_t vl0 = sb + OFF_VP - 1024 + blk0 * 2048 + (lm >> 1) * 1024 + lr * 128 + (((lm & 1) ^ lr) << 4);
      const uint32_t vl[4] = {vl0, vl0 ^ 64, vl0 ^ 32, vl0 ^ 96};
      const uint32_t obase = sb + OFF_OP + (wg == (rb2 & 1) ? 16384 : 0) + ((warp & 3) * 16 + lr) * 128 + ((lm ^ lr) << 4);
      mbar_wait(bars + 8 * BAR_STG, 0);
      {
        uint32_t km[4][4], va[8][4], vb[8][4], pp[8];
        float x[8][2];
#pragma unroll
        for (int n = 0; n < 4; n++) {
          const int blk = blk0 + 4 * (n >> 1);
          to_arr(km[n], lds128(sb + (blk == 0 ? OFF_L0 : OFF_KH + (blk - 1) * 2048) + (n & 1) * 512 + lane * 16));
        }
#pragma unroll
        for (int n = 0; n < 8; n++) {
          const uint32_t o = ((n >> 1) & 1) * 8192 + (n >> 2) * 1024;
          ldsm4t(va[n], vl[n & 1] + o);
          ldsm4t(vb[n], vl[2 + (n & 1)] + o);
        }
        const bool first = blk0 == 0 && gidx == 0;
#pragma unroll
        for (int n = 0; n < 4; n++) {
          const uint32_t(&q)[8] = qa[n >> 1][n & 1];
          float sm[4];
          mma16816_z(sm, q[0], q[1], q[2], q[3], km[n][0], km[n][1]);
          mma16816(sm, q[4], q[5], q[6], q[7], km[n][2], km[n][3]);
          if (n < 2 && first) sm[0] = sm[1] = -1e9f / 0.17677669529663687f;
          x[n][0] = le0 ? l[n >> 1][n & 1][0] : sm[0];
          x[n][1] = le1 ? l[n >> 1][n & 1][1] : sm[1];
          x[4 + n][0] = l[n >> 1][n & 1][2];
          x[4 + n][1] = l[n >> 1][n & 1][3];
        }
        quad_softmax<8>(x, pp);
#pragma unroll
        for (int n = 7; n >= 0; n--)
          attn_pv((obase ^ ((n & 1) << 6)) + ((n >> 1) & 1) * 8192 + (n >> 2) * 1024, va[n], vb[n], pp[n], maskLE);
      }
      fence_async_smem();
      nb_arrive(NB_OREADY + wg, 160);
    }

    {
      const int w = warp & 3;
      uint32_t a4[8][4];
      uint32_t d4[16];
      PROF(34 + wg);
      const uint64_t dz = mkdesc(sb + OFF_U + wg * 4096, 1024, 128, 0);
      const uint64_t db2 = mkdesc(sb + OFF_T + T_B2, 128, 256, 0);
      mbar_wait(bars + 8 * BAR_T, 0);
      mbar_wait(bars + 8 * BAR_UH, 0);
      to_arr(a1[0], lds128(tb + T_A1));
      to_arr(a1[1], lds128(tb + T_A1 + 2048));
      wg_fence();
      s1(0);
      ldtw(0);
      ldtw(1);
      const uint32_t za = sb + (w < 2 ? OFF_U : OFF_H) + wg * 4096 + (w & 1) * 8192 + lane * 16;
      const uint32_t yl = (wtid ^ (4 * rank + wg)) * 16;
      const uint32_t yown = mapa(sb, rank) + yl, yrem = mapa(sb + OFF_LAND + wg * 2048, rank ^ 1) + yl;
      const uint32_t yb[2] = {mapa(bars + 8 * BAR_LAND, 0), mapa(bars + 8 * BAR_LAND, 1)};
      wg_wait<0>();
      fence_regs(d1);
      auto s4 = [&]() {
        wg_fence();
#pragma unroll
        for (int ks = 0; ks < 8; ks++) {
          const uint64_t d = dz + (ks & 1) * 128 + ((ks >> 1) & 1) * 512 + (ks >> 2) * ((OFF_H - OFF_U) >> 4);
          if (ks == 0) hmma_n64t<0>(d4, a4[ks], d);
          else hmma_n64t<1>(d4, a4[ks], d);
        }
        wg_commit();
      };
      auto e4 = [&](int pr) {
        fence_regs(d4);
        mbar_wait(bars + 8 * (pr == 0 ? BAR_LFREE : BAR_DEAD + 1), 0);
#pragma unroll
        for (int u = 0; u < 2; u++) {
          const int it = 2 * pr + u;
          const uint32_t o = (yown + y_slot(wg, it)) ^ (pr << 5), m = (yrem + it * 4096) ^ (pr << 5);
          st_async128(rank ? m : o, yb[0], d4[8 * u], d4[8 * u + 1], d4[8 * u + 2], d4[8 * u + 3]);
          st_async128(rank ? o : m, yb[1], d4[8 * u + 4], d4[8 * u + 5], d4[8 * u + 6], d4[8 * u + 7]);
        }
      };
      uint32_t a2[2][2][2][4], a3[2][2][4], d2[2][2][8], d3[2][8];
      auto s2a = [&]() {
        wg_fence();
#pragma unroll
        for (int c = 0; c < 4; c++) hmma_n32<0, 0>(d2[c & 1][c >> 1], a2[0][c & 1][c >> 1], db2 + (c >> 1) * 128);
      };
      auto s2b = [&]() {
        wg_fence();
#pragma unroll
        for (int c = 0; c < 4; c++) {
          hmma_n32<1, 0>(d2[c & 1][c >> 1], a2[1][c & 1][c >> 1], db2 + (c >> 1) * 128 + 64);
          if (c & 1) wg_commit();
        }
      };
      fft_e1<0>(d1, tw, a2[0]);
      s2a();
      fft_e1<1>(d1, tw, a2[1]);
      s2b();
      s1(1);
      ldtw(2);
      ldtw(3);
#pragma unroll
      for (int i = 0; i < 8; i++) to_arr(a4[i], lds128(tb + T_A4 + i * 2048));
#pragma unroll
      for (int it = 0; it < 4; it++) {
        if (it == 2) wg_wait<3>(); else if (it == 3) wg_wait<1>(); else wg_wait<2>();
        fence_regs(d2[0][0]);
        fence_regs(d2[1][0]);
        fft_e2<0, 0>(d2[0][0], d2[1][0], a3[0]);
        fft_e2<0, 1>(d2[0][0], d2[1][0], a3[1]);
        if (it == 2) wg_wait<2>(); else if (it == 3) wg_wait<0>(); else wg_wait<1>();
        fence_regs(d2[0][1]);
        fence_regs(d2[1][1]);
        fft_e2<1, 0>(d2[0][1], d2[1][1], a3[0]);
        fft_e2<1, 1>(d2[0][1], d2[1][1], a3[1]);
        wg_fence();
        hmma_n32<0, 0>(d3[0], a3[0][0], db2);
        hmma_n32<0, 0>(d3[1], a3[0][1], db2);
        hmma_n32<1, 0>(d3[0], a3[1][0], db2 + 64);
        hmma_n32<1, 0>(d3[1], a3[1][1], db2 + 64);
        wg_commit();
        if (it < 3) {
          wg_wait<1>();
          if (it == 2) {
            if (wtid == 64) mbar_arrive(bars + 8 * BAR_DEAD);
            e4(0);
          }
          fence_regs(d1);
          fft_e1<0>(d1, tw, a2[0]);
        }
        wg_wait<0>();
        if (it == 3 && wtid == 64) mbar_arrive(bars + 8 * (BAR_DEAD + 1));
        fence_regs(d3[0]);
        fence_regs(d3[1]);
        if (it < 3) s2a();
        fft_e3(d3, tw, za + (it & 1) * 512);
        if (it < 3) {
          fft_e1<1>(d1, tw, a2[1]);
          s2b();
        }
        if (it & 1) {
          fence_async_smem();
          nb_sync(NB_WG + wg, 128);
          if (it == 1 && signaller) mbar_arrive_cluster(rbars + 8 * BAR_LFREE);
          s4();
        }
        if (it < 2) s1(it + 2);
        if (w == 0) PROF3(40 + 4 * wg + it);
      }
      if (PEEL && MODE == 0) {
        mbar_wait(bars + 8 * BAR_FULL2, 0);
        g2_step(0, 0);
        wg_wait<1>();
      } else {
        wg_wait<0>();
      }
      if (signaller) mbar_arrive_cluster(rbars + 8 * (BAR_EMPTY2 + 4));
      e4(1);
      if (PEEL && MODE == 0) {
        wg_wait<0>();
        if (signaller) mbar_arrive_cluster(rbars + 8 * BAR_EMPTY2);
      }
      PROF(6 + wg);
    }
    }

    if (MODE != 1) {
      int s = PEEL && MODE == 0, ph = 0;
#pragma unroll 1
      for (int kb = s; kb < STAG; kb++) {
        mbar_wait(bars + 8 * (BAR_FULL2 + s), ph);
        if (kb == 1) PROF(8 + wg);
        if (warp == 4) PROF2(40 + kb);
        g2_step(s, kb);
        wg_wait<0>();
        if (kb < 16 - NS2 && signaller) mbar_arrive_cluster(rbars + 8 * (BAR_EMPTY2 + s));
        if (++s == NS2) { s = 0; ph ^= 1; }
      }
      if (STAG < 16) {
        if (wg == LAST) nb_sync(NB_LEAD, 256);
#pragma unroll
        for (int kb = STAG; kb < 16; kb++) {
          mbar_wait(bars + 8 * (BAR_FULL2 + kb % NS2), (kb / NS2) & 1);
          g2_step(kb % NS2, 1);
        }
        if (wg != LAST) nb_arrive(NB_LEAD, 256);
      }
      wg_wait<0>();
      fence_regs(acc);
      PROF(10 + wg);
      const int lr = lane & 7, lm = lane >> 3;
      const uint32_t wbase = sb + warp * 2048;
      const uint32_t base = wbase + (lr + 8 * (lm & 1)) * 128;
#pragma unroll
      for (int j = 0; j < 16; j += 2) {
        const uint32_t a = base + (j >> 3) * 16384 + ((((j & 7) + (lm >> 1)) ^ lr) << 4);
        stsm4(a, pack_bf16(acc[4 * j], acc[4 * j + 1]), pack_bf16(acc[4 * j + 2], acc[4 * j + 3]),
              pack_bf16(acc[4 * j + 4], acc[4 * j + 5]), pack_bf16(acc[4 * j + 6], acc[4 * j + 7]));
      }
      __syncwarp();
      {
        const int rr = lane >> 4, ck = lane & 7, hf = (lane >> 3) & 1;
        uint4* og = reinterpret_cast<uint4*>(p.out + (size_t)(2 * ((rb2 & 7) * 128 + warp * 16 + rr) + (rb2 >> 3)) * (2 * DM) + DM + cb2 * 128 + hf * 64 + ck * 8);
        uint4 v[8];
#pragma unroll
        for (int i = 0; i < 8; i++) v[i] = lds128(wbase + hf * 16384 + (2 * i + rr) * 128 + ((ck ^ ((2 * i + rr) & 7)) << 4));
#pragma unroll
        for (int i = 0; i < 8; i++) og[(size_t)i * 4 * (2 * DM / 8)] = v[i];
      }
      PROF(12 + wg);
    }
    cluster_sync_all();
  }
}

typedef CUresult (*EncodeFn)(CUtensorMap*, CUtensorMapDataType, cuuint32_t, void*, const cuuint64_t*, const cuuint64_t*,
                             const cuuint32_t*, const cuuint32_t*, CUtensorMapInterleave, CUtensorMapSwizzle,
                             CUtensorMapL2promotion, CUtensorMapFloatOOBfill);

void make_map(EncodeFn enc, CUtensorMap* tm, const void* base, int rank, const cuuint64_t* dims, const cuuint64_t* strides,
              const cuuint32_t* box, CUtensorMapSwizzle swz) {
  cuuint32_t es[5] = {1, 1, 1, 1, 1};
  enc(tm, CU_TENSOR_MAP_DATA_TYPE_BFLOAT16, rank, const_cast<void*>(base), dims, strides, box, es,
      CU_TENSOR_MAP_INTERLEAVE_NONE, swz, CU_TENSOR_MAP_L2_PROMOTION_L2_256B, CU_TENSOR_MAP_FLOAT_OOB_FILL_NONE);
}

}

extern "C" void kernel_launch(void* const* d_in, const int* in_sizes, int n_in, void* d_out, int out_size) {
  static EncodeFn enc = nullptr;
  static bool coresident = true;
  if (!enc) {
    void* fn = nullptr;
    cudaDriverEntryPointQueryResult qr;
    cudaGetDriverEntryPoint("cuTensorMapEncodeTiled", &fn, cudaEnableDefault, &qr);
    enc = (EncodeFn)fn;
    cudaFuncSetAttribute(fused_kernel<0>, cudaFuncAttributeMaxDynamicSharedMemorySize, SMEM_BYTES);
    cudaFuncSetAttribute(fused_kernel<1>, cudaFuncAttributeMaxDynamicSharedMemorySize, SMEM_BYTES);
    cudaFuncSetAttribute(fused_kernel<2>, cudaFuncAttributeMaxDynamicSharedMemorySize, SMEM_BYTES);
    cudaLaunchConfig_t cfg = {};
    cfg.gridDim = dim3(NCTA);
    cfg.blockDim = dim3(NTHREADS);
    cfg.dynamicSmemBytes = SMEM_BYTES;
    cudaLaunchAttribute at;
    at.id = cudaLaunchAttributeClusterDimension;
    at.val.clusterDim.x = 2;
    at.val.clusterDim.y = 1;
    at.val.clusterDim.z = 1;
    cfg.attrs = &at;
    cfg.numAttrs = 1;
    int nclusters = 0;
    if (cudaOccupancyMaxActiveClusters(&nclusters, fused_kernel<0>, &cfg) == cudaSuccess) coresident = nclusters >= NCTA / 2;
    (void)cudaGetLastError();
  }
  CUtensorMap tmX, tmW, tmWo, tmQ, tmXh, tmWh;
  {
    cuuint64_t dims[3] = {1024, 2, 1024};
    cuuint64_t str[2] = {2048, 4096};
    cuuint32_t box[3] = {64, 1, 128};
    make_map(enc, &tmX, d_in[6], 3, dims, str, box, CU_TENSOR_MAP_SWIZZLE_128B);
  }
  {
    cuuint64_t dims[3] = {1024, 1024, 3};
    cuuint64_t str[2] = {6144, 2048};
    cuuint32_t box[3] = {64, 32, 3};
    make_map(enc, &tmW, d_in[7], 3, dims, str, box, CU_TENSOR_MAP_SWIZZLE_128B);
  }
  {
    cuuint64_t dims[3] = {64, 1024, 16};
    cuuint64_t str[2] = {2048, 128};
    cuuint32_t box[3] = {64, 64, 2};
    make_map(enc, &tmWo, d_in[8], 3, dims, str, box, CU_TENSOR_MAP_SWIZZLE_128B);
  }
  {
    cuuint64_t dims[5] = {1024, 2, 2, 8, 64};
    cuuint64_t str[4] = {2048, 16 * 2048, 2 * 2048, 32 * 2048};
    cuuint32_t box[5] = {16, 2, 2, 8, 4};
    make_map(enc, &tmQ, d_in[0], 5, dims, str, box, CU_TENSOR_MAP_SWIZZLE_NONE);
  }
  {
    cuuint64_t dims[4] = {1024, 256, 2, 4};
    cuuint64_t str[3] = {4096, 2048, 256 * 4096};
    cuuint32_t box[4] = {64, 8, 2, 4};
    make_map(enc, &tmXh, d_in[6], 4, dims, str, box, CU_TENSOR_MAP_SWIZZLE_128B);
  }
  {
    cuuint64_t dims[3] = {64, 1024, 48};
    cuuint64_t str[2] = {6144, 128};
    cuuint32_t box[3] = {64, 64, 4};
    make_map(enc, &tmWh, d_in[7], 3, dims, str, box, CU_TENSOR_MAP_SWIZZLE_128B);
  }
  Params p;
  p.q = (const __nv_bfloat16*)d_in[0];
  p.k = (const __nv_bfloat16*)d_in[1];
  p.v = (const __nv_bfloat16*)d_in[2];
  p.shift_k = (const __nv_bfloat16*)d_in[3];
  p.ssm_k = (const __nv_bfloat16*)d_in[4];
  p.ssm_D = (const __nv_bfloat16*)d_in[5];
  p.x = (const __nv_bfloat16*)d_in[6];
  p.w = (const __nv_bfloat16*)d_in[7];
  p.wo = (const __nv_bfloat16*)d_in[8];
  p.out = (__nv_bfloat16*)d_out;
  if (coresident) {
    fused_kernel<0><<<NCTA, NTHREADS, SMEM_BYTES>>>(p, tmX, tmW, tmWo, tmQ, tmXh, tmWh);
  } else {
    fused_kernel<0><<<4, NTHREADS, SMEM_BYTES>>>(p, tmX, tmW, tmWo, tmQ, tmXh, tmWh);
    fused_kernel<1><<<NCTA, NTHREADS, SMEM_BYTES>>>(p, tmX, tmW, tmWo, tmQ, tmXh, tmWh);
    fused_kernel<2><<<NCTA, NTHREADS, SMEM_BYTES>>>(p, tmX, tmW, tmWo, tmQ, tmXh, tmWh);
  }
}
```

```cpp
#include <cuda_runtime.h>
#include <cuda.h>
#include <cuda_bf16.h>
#include <stdint.h>

namespace {

constexpr int SEQ = 2048;
constexpr int DM = 1024;
constexpr int NCTA = 132;
constexpr int NTHREADS = 384;

constexpr int STG1A = 32768;
constexpr int NS1A = 3;
constexpr int STG1B = 12288;
constexpr int NS1B = 5;
constexpr int OFF_1B = NS1A * STG1A;
constexpr int STG2 = 32768;
constexpr int NS2 = 5;
constexpr int STGH = 73728;
constexpr int OFF_VP = 0;
constexpr int OFF_KH = 1 * STG2;
constexpr int OFF_OP = 2 * STG2;
constexpr int OFF_Q = 3 * STG2;
constexpr int T_A4 = 0, T_TW = 16384, T_B2 = 24576, T_A1 = 28672, T_END = 32768;
constexpr int OFF_U = 163840;
constexpr int OFF_H = OFF_U + 32768;
constexpr int OFF_T = OFF_U - T_END;
constexpr int OFF_LAND = 4 * STG2;
constexpr int OFF_BAR = OFF_H + 32768;
constexpr int OFF_SC = OFF_BAR + 512;
constexpr int OFF_L0 = -2048;
constexpr int SMEM_BYTES = 2048 + OFF_BAR + 1024;
static_assert(OFF_T + T_A1 == OFF_1B + NS1B * STG1B && OFF_T + T_TW == OFF_1B + 4 * STG1B && OFF_LAND == OFF_T + T_A4, "layout");
static_assert(3 * STGH <= OFF_BAR && SMEM_BYTES <= 232448, "smem");

constexpr int BAR_FULLA = 0;
constexpr int BAR_EMPTYA = 3;
constexpr int BAR_FULLB = 6;
constexpr int BAR_EMPTYB = 11;
constexpr int BAR_FULL2 = 16;
constexpr int BAR_EMPTY2 = 21;
constexpr int BAR_T = 26;
constexpr int BAR_UH = 27;
constexpr int BAR_LFREE = 28;
constexpr int BAR_LAND = 29;
constexpr int BAR_U = 30;
constexpr int BAR_Q = 31;
constexpr int BAR_STG = 32;
constexpr int BAR_DEAD = 33;
constexpr int BAR_X = 35;
constexpr int BAR_REL = 36;

constexpr int NB_G1DONE = 1;
constexpr int NB_OREADY = 2;
constexpr int NB_WG = 4;
constexpr int NB_HELP3 = 6;
constexpr int NB_FIRST = 7;
constexpr int NB_LEAD = 8;

#define PACE 390u
#define PF0 20
#define PEEL 1
#define IDLEW 1
#define LA0 3
#define LA1 4
#define STAG 12
#define LAST 0
#define FINE 40
#define F4 1
#define ORD 1
#define S1FIRST 0
#define REG_MATH 224
#define REG_HELP 56
constexpr int SPIN_LIMIT = 1 << 20;

__device__ __align__(1024) __nv_bfloat16 g_o[SEQ * DM];
__device__ __align__(128) uint32_t g_flag_o[256];
__device__ uint32_t g_flag_h[4];
__device__ uint4 g_halo[128 * 128];
__device__ __align__(128) const uint32_t g_tab[T_END / 4] = {
0x3c003c00,0x3bf13bff,0,0xafd6a648,0x3c003c00,0x3b993bce,0,0xb505b303,0x3c003c00,0x3af63b50,0,0xb7e3b67c,
0x3c003c00,0x3a0f3a8a,0,0xb93ab89b,0x3bc33bfe,0x3b773bfa,0xb3c6aa48,0xb5c2acb5,0x3a6d3b3b,0x389b3a4f,0xb8c4b6d7,0xba8ab8ec,
0x381d395f,0x26483505,0xbaddb9ed,0xbbffbb99,0x30b23564,0xb848b444,0xbbeabb88,0xbac2bbb6,0x3b0e3bf6,0x3a8a3bf1,0xb78bae46,0xb89bafd6,
0x34a53913,0xa6483732,0xbba8ba2f,0xbbffbb25,0xb78bae46,0xbac2b7e3,0xbb0ebbf6,0xb848baf6,0xbba8ba2f,0xbb50bbfa,0xb4a5b913,0x367cacb5,
0x39ed3bea,0x393a3be2,0xb95fb0b2,0xba0fb179,0xb56433c6,0xb8ec2648,0xbb88bbc3,0xba4fbbff,0xbbfeba6d,0xbb25bbce,0xaa48b8c4,0x3732b303,
0xb6d7badd,0x3444b67c,0x3b3b381d,0x3bb63b50,0x38723bd9,0x37323bce,0xbaa7b23e,0xbb25b303,0xbaa7b23e,0xbbb6b67c,0xb872bbd9,0xb444bb50,
0xb872bbd9,0xacb5ba8a,0x3aa7323e,0x3bfa389b,0x3aa7323e,0x3bf139cb,0x38723bd9,0xafd63984,0x35643bc3,0x33033bb6,0xbb88b3c6,0xbbceb444,
0xbbfeb8c4,0xbb77ba0f,0x2a48ba6d,0x35c2b93a,0x36d7b81d,0x3a8aafd6,0x3b3b3add,0x389b3bf1,0x395f3bea,0x26483b25,0xb9ed30b2,0xbbffb732,
0x2e463ba8,0xa6483b99,0xbbf6b4a5,0xbbffb505,0xba2fbb0e,0xb848bbb6,0x3913b78b,0x3ac2b444,0x3bf634a5,0x3b50393a,0x2e463ba8,0xb67c3a0f,
0xb913378b,0xbbe2afd6,0xba2fbb0e,0xb179bbf1,0xb0b23b88,0xb4443b77,0xbbeab564,0xbbb6b5c2,0xb3c6bbfe,0x2cb5bbe2,0x3bc3aa48,0x3bfa3179,
0x38c43b3b,0x2fd63bff,0xba6d36d7,0xbbf12648,0xbaddb95f,0xb505bbce,0x381db9ed,0x3b99b303,0xb61f3b64,0xb7e33b50,0xbb64b61f,0xbaf6b67c,
0x361fbb64,0x393aba8a,0x3b64361f,0x3a0f389b,0xb61f3b64,0xba4f3984,0xbb64b61f,0xb8ecb9cb,0x361fbb64,0x3b25b848,0x3b64361f,0x37323ac2,
0xb8c43b3b,0xb9843b25,0xba6db6d7,0xb9cbb732,0x3addb95f,0x3bceb7e3,0x381d39ed,0x33033af6,0xbbea3564,0xbb77acb5,0xb0b2bb88,0x35c2bbfa,
0x3bc32a48,0x389b38ec,0xb3c63bfe,0xba8a3a4f,0xba2f3b0e,0xbac23af6,0xb913b78b,0xb848b7e3,0x3bf6b4a5,0x3b50acb5,0xae463ba8,0xb67c3bfa,
0xb913b78b,0xb179ba4f,0x3a2fbb0e,0x3be2b8ec,0xae463ba8,0xb9cb3b99,0xbbf634a5,0xb984b505,0xbb3b3add,0xbb993ac2,0xb6d7b81d,0xb505b848,
0x39ed30b2,0x37e335c2,0xb95f3bea,0xbaf63b77,0x3564bbc3,0x3a0fbbe2,0x3b88b3c6,0x393a3179,0xbbfe38c4,0xba4f2648,0xaa48ba6d,0x38ecbbff,
0xbbd93aa7,0xbbfa3a8a,0xb23eb872,0xacb5b89b,0x323e3872,0xafd639cb,0xbbd93aa7,0xbbf13984,0x3bd9baa7,0x3b99b848,0x323e3872,0xb5053ac2,
0xb23eb872,0x37e3bb77,0x3bd9baa7,0x3af6b5c2,0xbbfe3a6d,0xbbe23a4f,0x2a48b8c4,0x3179b8ec,0xb6d73add,0xb9843b99,0xbb3b381d,0xb9cb3505,
0x395fb0b2,0x33033444,0xb9ed3bea,0xbbce3bb6,0x3b88bbc3,0x3b77b93a,0x356433c6,0xb5c23a0f,0xbba83a2f,0xbb503a0f,0x34a5b913,0x367cb93a,
0xbb0e3bf6,0xbbe23bf1,0xb78b2e46,0xb179afd6,0xb4a53913,0xb9cb3b25,0xbba83a2f,0xb9843732,0x378bae46,0xb30337e3,0xbb0e3bf6,0xbbce3af6,
0xbadd39ed,0xba4f39cb,0x381db95f,0x38ecb984,0xbbea3b88,0xbb253ac2,0x30b2b564,0x3732b848,0xbbc33bfe,0xbbb63b77,0xb3c62a48,0x3444b5c2,
0xba6d3b3b,0xbbfa3be2,0xb8c436d7,0x2cb5b179,0xb9a839a8,0xb8ec3984,0x39a8b9a8,0x3a4fb9cb,0xb9a839a8,0xb7323848,0x39a8b9a8,0x3b25bac2,
0xb9a839a8,0xb44435c2,0x39a8b9a8,0x3bb6bb77,0xb9a839a8,0xacb53179,0x39a8b9a8,0x3bfabbe2,0xb81d395f,0xb67c393a,0x3addb9ed,0x3b50ba0f,
0xb0b23564,0x31792fd6,0x3beabb88,0x3be2bbf1,0x33c6aa48,0x3984b732,0x3bc3bbfe,0x39cbbb25,0x38c4b6d7,0x3bcebaf6,0x3a6dbb3b,0x3303b7e3,
0xb4a53913,0xb17938ec,0x3ba8ba2f,0x3be2ba4f,0x378bae46,0x39cbb505,0x3b0ebbf6,0x3984bb99,0x3ba8ba2f,0x3bcebbb6,0x34a5b913,0xb303b444,
0x3b0ebbf6,0x35c2ba0f,0xb78b2e46,0xbb77393a,0xaa4838c4,0x2cb5389b,0x3bfeba6d,0x3bfaba8a,0x3b3bb81d,0x3bf1b984,0x36d7badd,0x2fd6b9cb,
0x39edbbea,0x3505bac2,0xb95f30b2,0xbb993848,0xb564b3c6,0xbaf635c2,0xbb883bc3,0xb7e33b77,0x323e3872,0x35053848,0x3bd9baa7,0x3b99bac2,
0x3bd9baa7,0x3af6bb77,0xb23eb872,0xb7e3b5c2,0xb23eb872,0xb93ab179,0xbbd93aa7,0xba0f3be2,0xbbd93aa7,0xb8ec3bff,0x323e3872,0x3a4fa648,
0x36d7381d,0x384837e3,0x3b3bbadd,0x3ac2baf6,0x395fbbea,0x367cbbfa,0xb9edb0b2,0xbb502cb5,0xbb8833c6,0xbbe238ec,0xb5643bc3,0x31793a4f,
0x2a483a6d,0x39843505,0x3bfeb8c4,0x39cbbb99,0x3913378b,0x39cb3732,0x3a2fbb0e,0x3984bb25,0x2e46bba8,0xb303baf6,0xbbf634a5,0xbbce37e3,
0xba2f3b0e,0xb5c23bfa,0x3913378b,0x3b772cb5,0x3bf6b4a5,0x3a8aba4f,0x2e46bba8,0xb89bb8ec,0x3a6d36d7,0x3af6367c,0x38c4bb3b,0x37e3bb50,
0xb81db9ed,0xba0fb89b,0xbadd395f,0xb93a3a8a,0x30b23b88,0x38ec39cb,0x3beab564,0x3a4fb984,0x33c6bbfe,0xb732bac2,0xbbc3aa48,0xbb253848,
0x3b64361f,0x3bb635c2,0x361fbb64,0x3444bb77,0xbb64b61f,0xbbfab179,0xb61f3b64,0xacb53be2,0x3b64361f,0x3bf1a648,0x361fbb64,0xafd6bbff,
0xbb64b61f,0xbb993303,0xb61f3b64,0x35053bce,0x3bea3564,0x3bff3505,0x30b2bb88,0x2648bb99,0xbbc32a48,0xbac23444,0x33c63bfe,0x38483bb6,
0x3a6db6d7,0x367cba0f,0xb8c4bb3b,0xbb50b93a,0xb81d39ed,0x31793bf1,0x3add395f,0x3be22fd6,0x3bf634a5,0x3bce3444,0xae46bba8,0xb303bbb6,
0xb913378b,0xb5c2393a,0x3a2f3b0e,0x3b773a0f,0xae46bba8,0xb89bbbf1,0xbbf6b4a5,0xba8a2fd6,0x3a2f3b0e,0x3bff3732,0x3913b78b,0xa648bb25,
0x3b8833c6,0x3b253303,0xb564bbc3,0xb732bbce,0xaa483a6d,0x34443b50,0x3bfe38c4,0x3bb6367c,0xbb3bbadd,0xbbfab89b,0xb6d7381d,0x2cb53a8a,
0x39edb0b2,0x2fd6b984,0xb95fbbea,0xbbf1b9cb,0x3aa7323e,0x3a0f3179,0xb872bbd9,0xb93abbe2,0x38723bd9,0x3a4f3bff,0x3aa7323e,0x38eca648,
0xbaa7b23e,0xb7323303,0x38723bd9,0x3b253bce,0xb872bbd9,0xbbb6bb50,0xbaa7b23e,0xb444367c,0x395f30b2,0x389b2fd6,0xb9edbbea,0xba8abbf1,
0x3b883bc3,0x3bff3b25,0x3564b3c6,0x2648b732,0x2a4838c4,0x38483af6,0x3bfe3a6d,0x3ac237e3,0xbb3bb81d,0xb67c2cb5,0x36d73add,0x3b503bfa,
0x378b2e46,0x35c22cb5,0xbb0ebbf6,0xbb77bbfa,0x3ba83a2f,0x3a8a38ec,0xb4a5b913,0xb89bba4f,0x3b0e3bf6,0x3bff3b99,0x378b2e46,0xa648b505,
0x34a53913,0x3ac23bb6,0x3ba83a2f,0x38483444,0x33c62a48,0x2fd62648,0xbbc3bbfe,0xbbf1bbff,0x38c436d7,0x35053303,0xba6dbb3b,0xbb99bbce,
0x3add39ed,0x37e3367c,0xb81db95f,0xbaf6bb50,0x3bea3b88,0x393a389b,0xb0b2b564,0xba0fba8a,0x3c003c00,0xbbf1bbff,0,0x2fd62648,
0x3c003c00,0xbb99bbce,0,0x35053303,0x3c003c00,0xbaf6bb50,0,0x37e3367c,0x3c003c00,0xba0fba8a,0,0x393a389b,
0x3bc33bfe,0xbb77bbfa,0xb3c6aa48,0x35c22cb5,0x3a6d3b3b,0xb89bba4f,0xb8c4b6d7,0x3a8a38ec,0x381d395f,0xa648b505,0xbaddb9ed,0x3bff3b99,
0x30b23564,0x38483444,0xbbeabb88,0x3ac23bb6,0x3b0e3bf6,0xba8abbf1,0xb78bae46,0x389b2fd6,0x34a53913,0x2648b732,0xbba8ba2f,0x3bff3b25,
0xb78bae46,0x3ac237e3,0xbb0ebbf6,0x38483af6,0xbba8ba2f,0x3b503bfa,0xb4a5b913,0xb67c2cb5,0x39ed3bea,0xb93abbe2,0xb95fb0b2,0x3a0f3179,
0xb56433c6,0x38eca648,0xbb88bbc3,0x3a4f3bff,0xbbfeba6d,0x3b253bce,0xaa48b8c4,0xb7323303,0xb6d7badd,0xb444367c,0x3b3b381d,0xbbb6bb50,
0x38723bd9,0xb732bbce,0xbaa7b23e,0x3b253303,0xbaa7b23e,0x3bb6367c,0xb872bbd9,0x34443b50,0xb872bbd9,0x2cb53a8a,0x3aa7323e,0xbbfab89b,
0x3aa7323e,0xbbf1b9cb,0x38723bd9,0x2fd6b984,0x35643bc3,0xb303bbb6,0xbb88b3c6,0x3bce3444,0xbbfeb8c4,0x3b773a0f,0x2a48ba6d,0xb5c2393a,
0x36d7b81d,0xba8a2fd6,0x3b3b3add,0xb89bbbf1,0x395f3bea,0xa648bb25,0xb9ed30b2,0x3bff3732,0x2e463ba8,0x2648bb99,0xbbf6b4a5,0x3bff3505,
0xba2fbb0e,0x38483bb6,0x3913b78b,0xbac23444,0x3bf634a5,0xbb50b93a,0x2e463ba8,0x367cba0f,0xb913378b,0x3be22fd6,0xba2fbb0e,0x31793bf1,
0xb0b23b88,0x3444bb77,0xbbeab564,0x3bb635c2,0xb3c6bbfe,0xacb53be2,0x3bc3aa48,0xbbfab179,0x38c43b3b,0xafd6bbff,0xba6d36d7,0x3bf1a648,
0xbaddb95f,0x35053bce,0x381db9ed,0xbb993303,0xb61f3b64,0x37e3bb50,0xbb64b61f,0x3af6367c,0x361fbb64,0xb93a3a8a,0x3b64361f,0xba0fb89b,
0xb61f3b64,0x3a4fb984,0xbb64b61f,0x38ec39cb,0x361fbb64,0xbb253848,0x3b64361f,0xb732bac2,0xb8c43b3b,0x3984bb25,0xba6db6d7,0x39cb3732,
0x3addb95f,0xbbce37e3,0x381d39ed,0xb303baf6,0xbbea3564,0x3b772cb5,0xb0b2bb88,0xb5c23bfa,0x3bc32a48,0xb89bb8ec,0xb3c63bfe,0x3a8aba4f,
0xba2f3b0e,0x3ac2baf6,0xb913b78b,0x384837e3,0x3bf6b4a5,0xbb502cb5,0xae463ba8,0x367cbbfa,0xb913b78b,0x31793a4f,0x3a2fbb0e,0xbbe238ec,
0xae463ba8,0x39cbbb99,0xbbf634a5,0x39843505,0xbb3b3add,0x3b99bac2,0xb6d7b81d,0x35053848,0x39ed30b2,0xb7e3b5c2,0xb95f3bea,0x3af6bb77,
0x3564bbc3,0xba0f3be2,0x3b88b3c6,0xb93ab179,0xbbfe38c4,0x3a4fa648,0xaa48ba6d,0xb8ec3bff,0xbbd93aa7,0x3bfaba8a,0xb23eb872,0x2cb5389b,
0x323e3872,0x2fd6b9cb,0xbbd93aa7,0x3bf1b984,0x3bd9baa7,0xbb993848,0x323e3872,0x3505bac2,0xb23eb872,0xb7e33b77,0x3bd9baa7,0xbaf635c2,
0xbbfe3a6d,0x3be2ba4f,0x2a48b8c4,0xb17938ec,0xb6d73add,0x3984bb99,0xbb3b381d,0x39cbb505,0x395fb0b2,0xb303b444,0xb9ed3bea,0x3bcebbb6,
0x3b88bbc3,0xbb77393a,0x356433c6,0x35c2ba0f,0xbba83a2f,0x3b50ba0f,0x34a5b913,0xb67c393a,0xbb0e3bf6,0x3be2bbf1,0xb78b2e46,0x31792fd6,
0xb4a53913,0x39cbbb25,0xbba83a2f,0x3984b732,0x378bae46,0x3303b7e3,0xbb0e3bf6,0x3bcebaf6,0xbadd39ed,0x3a4fb9cb,0x381db95f,0xb8ec3984,
0xbbea3b88,0x3b25bac2,0x30b2b564,0xb7323848,0xbbc33bfe,0x3bb6bb77,0xb3c62a48,0xb44435c2,0xba6d3b3b,0x3bfabbe2,0xb8c436d7,0xacb53179,
0xb9a839a8,0x38ecb984,0x39a8b9a8,0xba4f39cb,0xb9a839a8,0x3732b848,0x39a8b9a8,0xbb253ac2,0xb9a839a8,0x3444b5c2,0x39a8b9a8,0xbbb63b77,
0xb9a839a8,0x2cb5b179,0x39a8b9a8,0xbbfa3be2,0xb81d395f,0x367cb93a,0x3addb9ed,0xbb503a0f,0xb0b23564,0xb179afd6,0x3beabb88,0xbbe23bf1,
0x33c6aa48,0xb9843732,0x3bc3bbfe,0xb9cb3b25,0x38c4b6d7,0xbbce3af6,0x3a6dbb3b,0xb30337e3,0xb4a53913,0x3179b8ec,0x3ba8ba2f,0xbbe23a4f,
0x378bae46,0xb9cb3505,0x3b0ebbf6,0xb9843b99,0x3ba8ba2f,0xbbce3bb6,0x34a5b913,0x33033444,0x3b0ebbf6,0xb5c23a0f,0xb78b2e46,0x3b77b93a,
0xaa4838c4,0xacb5b89b,0x3bfeba6d,0xbbfa3a8a,0x3b3bb81d,0xbbf13984,0x36d7badd,0xafd639cb,0x39edbbea,0xb5053ac2,0xb95f30b2,0x3b99b848,
0xb564b3c6,0x3af6b5c2,0xbb883bc3,0x37e3bb77,0x323e3872,0xb505b848,0x3bd9baa7,0xbb993ac2,0x3bd9baa7,0xbaf63b77,0xb23eb872,0x37e335c2,
0xb23eb872,0x393a3179,0xbbd93aa7,0x3a0fbbe2,0xbbd93aa7,0x38ecbbff,0x323e3872,0xba4f2648,0x36d7381d,0xb848b7e3,0x3b3bbadd,0xbac23af6,
0x395fbbea,0xb67c3bfa,0xb9edb0b2,0x3b50acb5,0xbb8833c6,0x3be2b8ec,0xb5643bc3,0xb179ba4f,0x2a483a6d,0xb984b505,0x3bfeb8c4,0xb9cb3b99,
0x3913378b,0xb9cbb732,0x3a2fbb0e,0xb9843b25,0x2e46bba8,0x33033af6,0xbbf634a5,0x3bceb7e3,0xba2f3b0e,0x35c2bbfa,0x3913378b,0xbb77acb5,
0x3bf6b4a5,0xba8a3a4f,0x2e46bba8,0x389b38ec,0x3a6d36d7,0xbaf6b67c,0x38c4bb3b,0xb7e33b50,0xb81db9ed,0x3a0f389b,0xbadd395f,0x393aba8a,
0x30b23b88,0xb8ecb9cb,0x3beab564,0xba4f3984,0x33c6bbfe,0x37323ac2,0xbbc3aa48,0x3b25b848,0x3b64361f,0xbbb6b5c2,0x361fbb64,0xb4443b77,
0xbb64b61f,0x3bfa3179,0xb61f3b64,0x2cb5bbe2,0x3b64361f,0xbbf12648,0x361fbb64,0x2fd63bff,0xbb64b61f,0x3b99b303,0xb61f3b64,0xb505bbce,
0x3bea3564,0xbbffb505,0x30b2bb88,0xa6483b99,0xbbc32a48,0x3ac2b444,0x33c63bfe,0xb848bbb6,0x3a6db6d7,0xb67c3a0f,0xb8c4bb3b,0x3b50393a,
0xb81d39ed,0xb179bbf1,0x3add395f,0xbbe2afd6,0x3bf634a5,0xbbceb444,0xae46bba8,0x33033bb6,0xb913378b,0x35c2b93a,0x3a2f3b0e,0xbb77ba0f,
0xae46bba8,0x389b3bf1,0xbbf6b4a5,0x3a8aafd6,0x3a2f3b0e,0xbbffb732,0x3913b78b,0x26483b25,0x3b8833c6,0xbb25b303,0xb564bbc3,0x37323bce,
0xaa483a6d,0xb444bb50,0x3bfe38c4,0xbbb6b67c,0xbb3bbadd,0x3bfa389b,0xb6d7381d,0xacb5ba8a,0x39edb0b2,0xafd63984,0xb95fbbea,0x3bf139cb,
0x3aa7323e,0xba0fb179,0xb872bbd9,0x393a3be2,0x38723bd9,0xba4fbbff,0x3aa7323e,0xb8ec2648,0xbaa7b23e,0x3732b303,0x38723bd9,0xbb25bbce,
0xb872bbd9,0x3bb63b50,0xbaa7b23e,0x3444b67c,0x395f30b2,0xb89bafd6,0xb9edbbea,0x3a8a3bf1,0x3b883bc3,0xbbffbb25,0x3564b3c6,0xa6483732,
0x2a4838c4,0xb848baf6,0x3bfe3a6d,0xbac2b7e3,0xbb3bb81d,0x367cacb5,0x36d73add,0xbb50bbfa,0x378b2e46,0xb5c2acb5,0xbb0ebbf6,0x3b773bfa,
0x3ba83a2f,0xba8ab8ec,0xb4a5b913,0x389b3a4f,0x3b0e3bf6,0xbbffbb99,0x378b2e46,0x26483505,0x34a53913,0xbac2bbb6,0x3ba83a2f,0xb848b444,
0x33c62a48,0xafd6a648,0xbbc3bbfe,0x3bf13bff,0x38c436d7,0xb505b303,0xba6dbb3b,0x3b993bce,0x3add39ed,0xb7e3b67c,0xb81db95f,0x3af63b50,
0x3bea3b88,0xb93ab89b,0xb0b2b564,0x3a0f3a8a,0x3c003c00,0x38ec3984,0,0xba4fb9cb,0x3c003c00,0x37323848,0,0xbb25bac2,
0x3c003c00,0x344435c2,0,0xbbb6bb77,0x3c003c00,0x2cb53179,0,0xbbfabbe2,0xb3c6aa48,0xbb50ba0f,0xbbc3bbfe,0xb67cb93a,
0xb8c4b6d7,0xbbe2bbf1,0xba6dbb3b,0x3179afd6,0xbaddb9ed,0xb9cbbb25,0xb81db95f,0x39843732,0xbbeabb88,0xb303b7e3,0xb0b2b564,0x3bce3af6,
0xbb0ebbf6,0xb179b8ec,0x378b2e46,0x3be23a4f,0xb4a5b913,0x39cb3505,0x3ba83a2f,0x39843b99,0x378b2e46,0x3bce3bb6,0x3b0e3bf6,0xb3033444,
0x3ba83a2f,0x35c23a0f,0x34a53913,0xbb77b93a,0x395f30b2,0x3bfa3a8a,0x39ed3bea,0xacb5389b,0x3b883bc3,0x2fd639cb,0xb56433c6,0xbbf1b984,
0x2a4838c4,0xbb99b848,0xbbfeba6d,0xb505bac2,0xbb3bb81d,0xb7e3bb77,0xb6d7badd,0x3af635c2,0x38723bd9,0xb5053848,0xbaa7b23e,0xbb99bac2,
0xbaa7b23e,0xbaf6bb77,0xb872bbd9,0x37e3b5c2,0xb872bbd9,0x393ab179,0x3aa7323e,0x3a0f3be2,0x3aa7323e,0x38ec3bff,0x38723bd9,0xba4fa648,
0xbb88b3c6,0xbac2baf6,0xb564bbc3,0x3848b7e3,0x2a48ba6d,0x3b502cb5,0x3bfe38c4,0x367c3bfa,0x3b3b3add,0xb1793a4f,0xb6d7381d,0xbbe2b8ec,
0xb9ed30b2,0xb9cbbb99,0xb95fbbea,0x3984b505,0xae46bba8,0x39cbb732,0x3bf634a5,0x39843b25,0x3a2f3b0e,0xb3033af6,0xb913378b,0xbbceb7e3,
0xbbf6b4a5,0xb5c2bbfa,0xae46bba8,0x3b77acb5,0x3913b78b,0x3a8a3a4f,0x3a2f3b0e,0xb89b38ec,0x3bea3564,0x37e33b50,0xb0b23b88,0xbaf6367c,
0xbbc32a48,0xb93aba8a,0xb3c6bbfe,0x3a0fb89b,0x3a6db6d7,0x3a4f3984,0x38c43b3b,0xb8ec39cb,0xb81d39ed,0xbb25b848,0xbaddb95f,0x3732bac2,
0xb61f3b64,0xbbb635c2,0xbb64b61f,0xb444bb77,0x361fbb64,0x3bfab179,0x3b64361f,0x2cb53be2,0xb61f3b64,0xbbf1a648,0xbb64b61f,0x2fd6bbff,
0x361fbb64,0x3b993303,0x3b64361f,0xb5053bce,0xba6db6d7,0xa648bb99,0x38c4bb3b,0x3bffb505,0x381d39ed,0xb8483bb6,0xbadd395f,0xbac2b444,
0xb0b2bb88,0x3b50b93a,0x3beab564,0x367c3a0f,0xb3c63bfe,0xbbe22fd6,0xbbc3aa48,0x3179bbf1,0x3a2fbb0e,0x3bceb444,0x3913378b,0xb3033bb6,
0xbbf634a5,0xb5c2b93a,0x2e46bba8,0x3b77ba0f,0x3913378b,0xb89b3bf1,0xba2f3b0e,0xba8aafd6,0x2e46bba8,0x3bffb732,0x3bf6b4a5,0xa6483b25,
0x36d7381d,0xb7323bce,0xbb3b3add,0xbb253303,0x395fbbea,0x3bb6b67c,0x39ed30b2,0xb4443b50,0xbb8833c6,0x2cb5ba8a,0x3564bbc3,0x3bfab89b,
0x2a483a6d,0xbbf139cb,0xbbfe38c4,0xafd6b984,0xbbd93aa7,0xba0f3179,0xb23eb872,0x393abbe2,0x323e3872,0xba4f3bff,0xbbd93aa7,0xb8eca648,
0x3bd9baa7,0x37323303,0x323e3872,0xbb253bce,0xb23eb872,0x3bb6bb50,0x3bd9baa7,0x3444367c,0x2a48b8c4,0x3a8abbf1,0x3bfeba6d,0x389bafd6,
0xbb3b381d,0xa648b732,0x36d7badd,0x3bffbb25,0xb9ed3bea,0xbac237e3,0xb95f30b2,0x3848baf6,0x356433c6,0xbb503bfa,0xbb883bc3,0xb67cacb5,
0x3ba8ba2f,0x35c2acb5,0xb4a53913,0xbb773bfa,0x3b0ebbf6,0x3a8ab8ec,0x378bae46,0xb89b3a4f,0x34a5b913,0x3bffbb99,0x3ba8ba2f,0xa6483505,
0xb78b2e46,0x3ac2bbb6,0x3b0ebbf6,0x3848b444,0xb81d395f,0xbbf13bff,0xbadd39ed,0xafd62648,0xb0b23564,0xbb993bce,0xbbea3b88,0xb5053303,
0x33c6aa48,0xbaf63b50,0xbbc33bfe,0xb7e3367c,0x38c4b6d7,0xba0f3a8a,0xba6d3b3b,0xb93a389b,0xb9a839a8,0x2fd6a648,0x39a8b9a8,0x3bf1bbff,
0xb9a839a8,0x3505b303,0x39a8b9a8,0x3b99bbce,0xb9a839a8,0x37e3b67c,0x39a8b9a8,0x3af6bb50,0xb9a839a8,0x393ab89b,0x39a8b9a8,0x3a0fba8a,
0x3addb9ed,0x3b77bbfa,0x381db95f,0xb5c22cb5,0x3beabb88,0x389bba4f,0x30b2b564,0xba8a38ec,0x3bc3bbfe,0x2648b505,0xb3c62a48,0xbbff3b99,
0x3a6dbb3b,0xb8483444,0xb8c436d7,0xbac23bb6,0x34a5b913,0xb89b2fd6,0xbba83a2f,0xba8a3bf1,0xb78b2e46,0xbbff3b25,0xbb0e3bf6,0x26483732,
0xbba83a2f,0xb8483af6,0xb4a53913,0x3ac2b7e3,0xbb0e3bf6,0x367c2cb5,0x378bae46,0x3b50bbfa,0xbbfe3a6d,0xb93a3be2,0xaa4838c4,0x3a0fb179,
0xb6d73add,0x38ec2648,0x3b3bb81d,0x3a4fbbff,0x395fb0b2,0x3b25bbce,0x39edbbea,0xb732b303,0x3b88bbc3,0xb444b67c,0xb564b3c6,0xbbb63b50,
0x323e3872,0x3b25b303,0x3bd9baa7,0x3732bbce,0x3bd9baa7,0x3444bb50,0xb23eb872,0xbbb6367c,0xb23eb872,0xbbfa389b,0xbbd93aa7,0xacb53a8a,
0xbbd93aa7,0x2fd63984,0x323e3872,0x3bf1b9cb,0x3b3bbadd,0x3303bbb6,0xb6d7b81d,0xbbce3444,0xb9edb0b2,0xbb773a0f,0xb95f3bea,0x35c2393a,
0xb5643bc3,0x3a8a2fd6,0x3b88b3c6,0x389bbbf1,0x3bfeb8c4,0x2648bb25,0xaa48ba6d,0xbbff3732,0xb913b78b,0xbbff3505,0xba2f3b0e,0x26483b99,
0xae463ba8,0x3ac23444,0x3bf6b4a5,0x3848bbb6,0x3a2fbb0e,0xb67cba0f,0xb913b78b,0xbb50393a,0xbbf634a5,0xb1793bf1,0xae463ba8,0x3be2afd6,
0xb8c43b3b,0x34443b77,0x3a6d36d7,0x3bb6b5c2,0x3addb95f,0xacb5bbe2,0xb81db9ed,0xbbfa3179,0xbbea3564,0xafd63bff,0x30b23b88,0x3bf12648,
0x3bc32a48,0x3505bbce,0x33c6bbfe,0xbb99b303,0x3b64361f,0x3af6b67c,0x361fbb64,0xb7e3bb50,0xbb64b61f,0xba0f389b,0xb61f3b64,0x393a3a8a,
0x3b64361f,0x38ecb9cb,0x361fbb64,0xba4fb984,0xbb64b61f,0xb7323ac2,0xb61f3b64,0x3b253848,0x30b2bb88,0xb984bb25,0xbbeab564,0xb9cb3732,
0x33c63bfe,0x3bce37e3,0x3bc3aa48,0x3303baf6,0xb8c4bb3b,0xbb772cb5,0xba6d36d7,0x35c23bfa,0x3add395f,0x389bb8ec,0x381db9ed,0xba8aba4f,
0xbbf6b4a5,0xb84837e3,0x2e463ba8,0x3ac23af6,0x3913b78b,0xb67cbbfa,0xba2fbb0e,0xbb50acb5,0x2e463ba8,0x3be238ec,0x3bf634a5,0x3179ba4f,
0xba2fbb0e,0xb9843505,0xb913378b,0x39cb3b99,0x35643bc3,0x3b993ac2,0x3b8833c6,0x3505b848,0xbbfeb8c4,0xb7e335c2,0xaa483a6d,0x3af63b77,
0x36d7b81d,0xba0fbbe2,0xbb3bbadd,0xb93a3179,0x395f3bea,0x3a4f2648,0x39edb0b2,0xb8ecbbff,0x3aa7323e,0x2cb5b89b,0xb872bbd9,0xbbfaba8a,
0x38723bd9,0x3bf13984,0x3aa7323e,0xafd6b9cb,0xbaa7b23e,0x35053ac2,0x38723bd9,0x3b993848,0xb872bbd9,0xbaf6b5c2,0xbaa7b23e,0x37e33b77,
0xb9edbbea,0xbbe2ba4f,0xb95fb0b2,0x317938ec,0x3564b3c6,0xb984bb99,0xbb88bbc3,0xb9cbb505,0x3bfe3a6d,0x3303b444,0xaa48b8c4,0xbbcebbb6,
0x36d73add,0x3b77393a,0x3b3b381d,0xb5c2ba0f,0xb78bae46,0x367c393a,0x3b0e3bf6,0x3b503a0f,0xbba8ba2f,0xb1792fd6,0x34a53913,0x3be23bf1,
0xbb0ebbf6,0xb984b732,0xb78bae46,0x39cb3b25,0xb4a5b913,0xbbcebaf6,0xbba8ba2f,0x330337e3,0x3bc33bfe,0x3a4f39cb,0x33c62a48,0xb8ecb984,
0x3a6d3b3b,0x3b253ac2,0x38c436d7,0xb732b848,0x381d395f,0x3bb63b77,0x3add39ed,0xb444b5c2,0x30b23564,0x3bfa3be2,0x3bea3b88,0xacb5b179,
0x3c003c00,0xb8ecb984,0,0x3a4f39cb,0x3c003c00,0xb732b848,0,0x3b253ac2,0x3c003c00,0xb444b5c2,0,0x3bb63b77,
0x3c003c00,0xacb5b179,0,0x3bfa3be2,0xb3c6aa48,0x3b503a0f,0xbbc3bbfe,0x367c393a,0xb8c4b6d7,0x3be23bf1,0xba6dbb3b,0xb1792fd6,
0xbaddb9ed,0x39cb3b25,0xb81db95f,0xb984b732,0xbbeabb88,0x330337e3,0xb0b2b564,0xbbcebaf6,0xbb0ebbf6,0x317938ec,0x378b2e46,0xbbe2ba4f,
0xb4a5b913,0xb9cbb505,0x3ba83a2f,0xb984bb99,0x378b2e46,0xbbcebbb6,0x3b0e3bf6,0x3303b444,0x3ba83a2f,0xb5c2ba0f,0x34a53913,0x3b77393a,
0x395f30b2,0xbbfaba8a,0x39ed3bea,0x2cb5b89b,0x3b883bc3,0xafd6b9cb,0xb56433c6,0x3bf13984,0x2a4838c4,0x3b993848,0xbbfeba6d,0x35053ac2,
0xbb3bb81d,0x37e33b77,0xb6d7badd,0xbaf6b5c2,0x38723bd9,0x3505b848,0xbaa7b23e,0x3b993ac2,0xbaa7b23e,0x3af63b77,0xb872bbd9,0xb7e335c2,
0xb872bbd9,0xb93a3179,0x3aa7323e,0xba0fbbe2,0x3aa7323e,0xb8ecbbff,0x38723bd9,0x3a4f2648,0xbb88b3c6,0x3ac23af6,0xb564bbc3,0xb84837e3,
0x2a48ba6d,0xbb50acb5,0x3bfe38c4,0xb67cbbfa,0x3b3b3add,0x3179ba4f,0xb6d7381d,0x3be238ec,0xb9ed30b2,0x39cb3b99,0xb95fbbea,0xb9843505,
0xae46bba8,0xb9cb3732,0x3bf634a5,0xb984bb25,0x3a2f3b0e,0x3303baf6,0xb913378b,0x3bce37e3,0xbbf6b4a5,0x35c23bfa,0xae46bba8,0xbb772cb5,
0x3913b78b,0xba8aba4f,0x3a2f3b0e,0x389bb8ec,0x3bea3564,0xb7e3bb50,0xb0b23b88,0x3af6b67c,0xbbc32a48,0x393a3a8a,0xb3c6bbfe,0xba0f389b,
0x3a6db6d7,0xba4fb984,0x38c43b3b,0x38ecb9cb,0xb81d39ed,0x3b253848,0xbaddb95f,0xb7323ac2,0xb61f3b64,0x3bb6b5c2,0xbb64b61f,0x34443b77,
0x361fbb64,0xbbfa3179,0x3b64361f,0xacb5bbe2,0xb61f3b64,0x3bf12648,0xbb64b61f,0xafd63bff,0x361fbb64,0xbb99b303,0x3b64361f,0x3505bbce,
0xba6db6d7,0x26483b99,0x38c4bb3b,0xbbff3505,0x381d39ed,0x3848bbb6,0xbadd395f,0x3ac23444,0xb0b2bb88,0xbb50393a,0x3beab564,0xb67cba0f,
0xb3c63bfe,0x3be2afd6,0xbbc3aa48,0xb1793bf1,0x3a2fbb0e,0xbbce3444,0x3913378b,0x3303bbb6,0xbbf634a5,0x35c2393a,0x2e46bba8,0xbb773a0f,
0x3913378b,0x389bbbf1,0xba2f3b0e,0x3a8a2fd6,0x2e46bba8,0xbbff3732,0x3bf6b4a5,0x2648bb25,0x36d7381d,0x3732bbce,0xbb3b3add,0x3b25b303,
0x395fbbea,0xbbb6367c,0x39ed30b2,0x3444bb50,0xbb8833c6,0xacb53a8a,0x3564bbc3,0xbbfa389b,0x2a483a6d,0x3bf1b9cb,0xbbfe38c4,0x2fd63984,
0xbbd93aa7,0x3a0fb179,0xb23eb872,0xb93a3be2,0x323e3872,0x3a4fbbff,0xbbd93aa7,0x38ec2648,0x3bd9baa7,0xb732b303,0x323e3872,0x3b25bbce,
0xb23eb872,0xbbb63b50,0x3bd9baa7,0xb444b67c,0x2a48b8c4,0xba8a3bf1,0x3bfeba6d,0xb89b2fd6,0xbb3b381d,0x26483732,0x36d7badd,0xbbff3b25,
0xb9ed3bea,0x3ac2b7e3,0xb95f30b2,0xb8483af6,0x356433c6,0x3b50bbfa,0xbb883bc3,0x367c2cb5,0x3ba8ba2f,0xb5c22cb5,0xb4a53913,0x3b77bbfa,
0x3b0ebbf6,0xba8a38ec,0x378bae46,0x389bba4f,0x34a5b913,0xbbff3b99,0x3ba8ba2f,0x2648b505,0xb78b2e46,0xbac23bb6,0x3b0ebbf6,0xb8483444,
0xb81d395f,0x3bf1bbff,0xbadd39ed,0x2fd6a648,0xb0b23564,0x3b99bbce,0xbbea3b88,0x3505b303,0x33c6aa48,0x3af6bb50,0xbbc33bfe,0x37e3b67c,
0x38c4b6d7,0x3a0fba8a,0xba6d3b3b,0x393ab89b,0xb9a839a8,0xafd62648,0x39a8b9a8,0xbbf13bff,0xb9a839a8,0xb5053303,0x39a8b9a8,0xbb993bce,
0xb9a839a8,0xb7e3367c,0x39a8b9a8,0xbaf63b50,0xb9a839a8,0xb93a389b,0x39a8b9a8,0xba0f3a8a,0x3addb9ed,0xbb773bfa,0x381db95f,0x35c2acb5,
0x3beabb88,0xb89b3a4f,0x30b2b564,0x3a8ab8ec,0x3bc3bbfe,0xa6483505,0xb3c62a48,0x3bffbb99,0x3a6dbb3b,0x3848b444,0xb8c436d7,0x3ac2bbb6,
0x34a5b913,0x389bafd6,0xbba83a2f,0x3a8abbf1,0xb78b2e46,0x3bffbb25,0xbb0e3bf6,0xa648b732,0xbba83a2f,0x3848baf6,0xb4a53913,0xbac237e3,
0xbb0e3bf6,0xb67cacb5,0x378bae46,0xbb503bfa,0xbbfe3a6d,0x393abbe2,0xaa4838c4,0xba0f3179,0xb6d73add,0xb8eca648,0x3b3bb81d,0xba4f3bff,
0x395fb0b2,0xbb253bce,0x39edbbea,0x37323303,0x3b88bbc3,0x3444367c,0xb564b3c6,0x3bb6bb50,0x323e3872,0xbb253303,0x3bd9baa7,0xb7323bce,
0x3bd9baa7,0xb4443b50,0xb23eb872,0x3bb6b67c,0xb23eb872,0x3bfab89b,0xbbd93aa7,0x2cb5ba8a,0xbbd93aa7,0xafd6b984,0x323e3872,0xbbf139cb,
0x3b3bbadd,0xb3033bb6,0xb6d7b81d,0x3bceb444,0xb9edb0b2,0x3b77ba0f,0xb95f3bea,0xb5c2b93a,0xb5643bc3,0xba8aafd6,0x3b88b3c6,0xb89b3bf1,
0x3bfeb8c4,0xa6483b25,0xaa48ba6d,0x3bffb732,0xb913b78b,0x3bffb505,0xba2f3b0e,0xa648bb99,0xae463ba8,0xbac2b444,0x3bf6b4a5,0xb8483bb6,
0x3a2fbb0e,0x367c3a0f,0xb913b78b,0x3b50b93a,0xbbf634a5,0x3179bbf1,0xae463ba8,0xbbe22fd6,0xb8c43b3b,0xb444bb77,0x3a6d36d7,0xbbb635c2,
0x3addb95f,0x2cb53be2,0xb81db9ed,0x3bfab179,0xbbea3564,0x2fd6bbff,0x30b23b88,0xbbf1a648,0x3bc32a48,0xb5053bce,0x33c6bbfe,0x3b993303,
0x3b64361f,0xbaf6367c,0x361fbb64,0x37e33b50,0xbb64b61f,0x3a0fb89b,0xb61f3b64,0xb93aba8a,0x3b64361f,0xb8ec39cb,0x361fbb64,0x3a4f3984,
0xbb64b61f,0x3732bac2,0xb61f3b64,0xbb25b848,0x30b2bb88,0x39843b25,0xbbeab564,0x39cbb732,0x33c63bfe,0xbbceb7e3,0x3bc3aa48,0xb3033af6,
0xb8c4bb3b,0x3b77acb5,0xba6d36d7,0xb5c2bbfa,0x3add395f,0xb89b38ec,0x381db9ed,0x3a8a3a4f,0xbbf6b4a5,0x3848b7e3,0x2e463ba8,0xbac2baf6,
0x3913b78b,0x367c3bfa,0xba2fbb0e,0x3b502cb5,0x2e463ba8,0xbbe2b8ec,0x3bf634a5,0xb1793a4f,0xba2fbb0e,0x3984b505,0xb913378b,0xb9cbbb99,
0x35643bc3,0xbb99bac2,0x3b8833c6,0xb5053848,0xbbfeb8c4,0x37e3b5c2,0xaa483a6d,0xbaf6bb77,0x36d7b81d,0x3a0f3be2,0xbb3bbadd,0x393ab179,
0x395f3bea,0xba4fa648,0x39edb0b2,0x38ec3bff,0x3aa7323e,0xacb5389b,0xb872bbd9,0x3bfa3a8a,0x38723bd9,0xbbf1b984,0x3aa7323e,0x2fd639cb,
0xbaa7b23e,0xb505bac2,0x38723bd9,0xbb99b848,0xb872bbd9,0x3af635c2,0xbaa7b23e,0xb7e3bb77,0xb9edbbea,0x3be23a4f,0xb95fb0b2,0xb179b8ec,
0x3564b3c6,0x39843b99,0xbb88bbc3,0x39cb3505,0x3bfe3a6d,0xb3033444,0xaa48b8c4,0x3bce3bb6,0x36d73add,0xbb77b93a,0x3b3b381d,0x35c23a0f,
0xb78bae46,0xb67cb93a,0x3b0e3bf6,0xbb50ba0f,0xbba8ba2f,0x3179afd6,0x34a53913,0xbbe2bbf1,0xbb0ebbf6,0x39843732,0xb78bae46,0xb9cbbb25,
0xb4a5b913,0x3bce3af6,0xbba8ba2f,0xb303b7e3,0x3bc33bfe,0xba4fb9cb,0x33c62a48,0x38ec3984,0x3a6d3b3b,0xbb25bac2,0x38c436d7,0x37323848,
0x381d395f,0xbbb6bb77,0x3add39ed,0x344435c2,0x30b23564,0xbbfabbe2,0x3bea3b88,0x2cb53179,0x3c003c00,0xafd6a648,0,0xbbf1bbff,
0x3c003c00,0xb505b303,0,0xbb99bbce,0x3c003c00,0xb7e3b67c,0,0xbaf6bb50,0x3c003c00,0xb93ab89b,0,0xba0fba8a,
0xbbc3bbfe,0x35c22cb5,0x33c62a48,0x3b773bfa,0xba6dbb3b,0x3a8a38ec,0x38c436d7,0x389b3a4f,0xb81db95f,0x3bff3b99,0x3add39ed,0x26483505,
0xb0b2b564,0x3ac23bb6,0x3bea3b88,0xb848b444,0x3b0e3bf6,0xb89bafd6,0xb78bae46,0xba8abbf1,0x34a53913,0xbbffbb25,0xbba8ba2f,0x2648b732,
0xb78bae46,0xb848baf6,0xbb0ebbf6,0x3ac237e3,0xbba8ba2f,0x367cacb5,0xb4a5b913,0x3b503bfa,0xb9edbbea,0x3a0f3179,0x395f30b2,0x393a3be2,
0x3564b3c6,0x3a4f3bff,0x3b883bc3,0xb8ec2648,0x3bfe3a6d,0xb7323303,0x2a4838c4,0xbb25bbce,0x36d73add,0xbbb6bb50,0xbb3bb81d,0x3444b67c,
0x38723bd9,0xbb25b303,0xbaa7b23e,0xb732bbce,0xbaa7b23e,0xb444bb50,0xb872bbd9,0x3bb6367c,0xb872bbd9,0x3bfa389b,0x3aa7323e,0x2cb53a8a,
0x3aa7323e,0xafd63984,0x38723bd9,0xbbf1b9cb,0xb564bbc3,0x3bce3444,0x3b8833c6,0x33033bb6,0x3bfe38c4,0xb5c2393a,0xaa483a6d,0xbb77ba0f,
0xb6d7381d,0xb89bbbf1,0xbb3bbadd,0x3a8aafd6,0xb95fbbea,0x3bff3732,0x39edb0b2,0x26483b25,0x2e463ba8,0xbbffb505,0xbbf6b4a5,0x2648bb99,
0xba2fbb0e,0x3ac2b444,0x3913b78b,0x38483bb6,0x3bf634a5,0xb67c3a0f,0x2e463ba8,0xbb50b93a,0xb913378b,0xb179bbf1,0xba2fbb0e,0x3be22fd6,
0x30b2bb88,0x3bb635c2,0x3bea3564,0xb4443b77,0x33c63bfe,0xbbfab179,0xbbc32a48,0x2cb5bbe2,0xb8c4bb3b,0x3bf1a648,0x3a6db6d7,0x2fd63bff,
0x3add395f,0xbb993303,0xb81d39ed,0xb505bbce,0xb61f3b64,0xbaf6b67c,0xbb64b61f,0x37e3bb50,0x361fbb64,0x3a0f389b,0x3b64361f,0xb93a3a8a,
0xb61f3b64,0xb8ecb9cb,0xbb64b61f,0x3a4fb984,0x361fbb64,0x37323ac2,0x3b64361f,0xbb253848,0x38c4bb3b,0x39cb3732,0x3a6d36d7,0xb9843b25,
0xbadd395f,0xb303baf6,0xb81db9ed,0x3bceb7e3,0x3beab564,0xb5c23bfa,0x30b23b88,0xbb77acb5,0xbbc3aa48,0x3a8aba4f,0x33c6bbfe,0x389b38ec,
0xba2f3b0e,0xb848b7e3,0xb913b78b,0x3ac2baf6,0x3bf6b4a5,0xb67c3bfa,0xae463ba8,0xbb502cb5,0xb913b78b,0x3be2b8ec,0x3a2fbb0e,0x31793a4f,
0xae463ba8,0xb984b505,0xbbf634a5,0x39cbbb99,0x3b3bbadd,0x35053848,0x36d7381d,0xbb993ac2,0xb9edb0b2,0x3af6bb77,0x395fbbea,0x37e335c2,
0xb5643bc3,0xb93ab179,0xbb8833c6,0x3a0fbbe2,0x3bfeb8c4,0xb8ec3bff,0x2a483a6d,0xba4f2648,0xbbd93aa7,0xacb5b89b,0xb23eb872,0x3bfaba8a,
0x323e3872,0xbbf13984,0xbbd93aa7,0x2fd6b9cb,0x3bd9baa7,0xb5053ac2,0x323e3872,0xbb993848,0xb23eb872,0x3af6b5c2,0x3bd9baa7,0xb7e33b77,
0x3bfeba6d,0xb17938ec,0xaa4838c4,0xbbe23a4f,0x36d7badd,0x39cbb505,0x3b3bb81d,0xb9843b99,0xb95f30b2,0x3bcebbb6,0x39edbbea,0x33033444,
0xbb883bc3,0x35c2ba0f,0xb564b3c6,0x3b77b93a,0xbba83a2f,0x367cb93a,0x34a5b913,0x3b50ba0f,0xbb0e3bf6,0xb179afd6,0xb78b2e46,0x3be2bbf1,
0xb4a53913,0xb9843732,0xbba83a2f,0x39cbbb25,0x378bae46,0xbbce3af6,0xbb0e3bf6,0x3303b7e3,0x3addb9ed,0xb8ec3984,0xb81d395f,0xba4f39cb,
0x3beabb88,0xb7323848,0xb0b23564,0xbb253ac2,0x3bc3bbfe,0xb44435c2,0x33c6aa48,0xbbb63b77,0x3a6dbb3b,0xacb53179,0x38c4b6d7,0xbbfa3be2,
0xb9a839a8,0x3a4fb9cb,0x39a8b9a8,0x38ecb984,0xb9a839a8,0x3b25bac2,0x39a8b9a8,0x3732b848,0xb9a839a8,0x3bb6bb77,0x39a8b9a8,0x3444b5c2,
0xb9a839a8,0x3bfabbe2,0x39a8b9a8,0x2cb5b179,0x381db95f,0xbb503a0f,0xbadd39ed,0xb67c393a,0x30b2b564,0xbbe23bf1,0xbbea3b88,0x31792fd6,
0xb3c62a48,0xb9cb3b25,0xbbc33bfe,0x3984b732,0xb8c436d7,0xb30337e3,0xba6d3b3b,0x3bcebaf6,0xb4a53913,0x3be2ba4f,0x3ba8ba2f,0x3179b8ec,
0x378bae46,0x3984bb99,0x3b0ebbf6,0xb9cb3505,0x3ba8ba2f,0xb303b444,0x34a5b913,0xbbce3bb6,0x3b0ebbf6,0xbb77393a,0xb78b2e46,0xb5c23a0f,
0x2a48b8c4,0xbbfa3a8a,0xbbfe3a6d,0x2cb5389b,0xbb3b381d,0xafd639cb,0xb6d73add,0x3bf1b984,0xb9ed3bea,0x3b99b848,0x395fb0b2,0x3505bac2,
0x356433c6,0x37e3bb77,0x3b88bbc3,0xbaf635c2,0x323e3872,0x3b99bac2,0x3bd9baa7,0xb505b848,0x3bd9baa7,0xb7e3b5c2,0xb23eb872,0xbaf63b77,
0xb23eb872,0xba0f3be2,0xbbd93aa7,0x393a3179,0xbbd93aa7,0x3a4fa648,0x323e3872,0x38ecbbff,0xb6d7b81d,0xbac23af6,0xbb3b3add,0x384837e3,
0xb95f3bea,0x3b50acb5,0x39ed30b2,0x367cbbfa,0x3b88b3c6,0xb179ba4f,0x3564bbc3,0xbbe238ec,0xaa48ba6d,0xb9cb3b99,0xbbfe38c4,0x39843505,
0x3913378b,0x3984bb25,0x3a2fbb0e,0xb9cbb732,0x2e46bba8,0xbbce37e3,0xbbf634a5,0x33033af6,0xba2f3b0e,0x3b772cb5,0x3913378b,0x35c2bbfa,
0x3bf6b4a5,0xb89bb8ec,0x2e46bba8,0xba8a3a4f,0xba6db6d7,0xb7e33b50,0xb8c43b3b,0x3af6367c,0x381d39ed,0x393aba8a,0x3addb95f,0xba0fb89b,
0xb0b2bb88,0xba4f3984,0xbbea3564,0x38ec39cb,0xb3c63bfe,0x3b25b848,0x3bc32a48,0xb732bac2,0x3b64361f,0x3444bb77,0x361fbb64,0xbbb6b5c2,
0xbb64b61f,0xacb53be2,0xb61f3b64,0x3bfa3179,0x3b64361f,0xafd6bbff,0x361fbb64,0xbbf12648,0xbb64b61f,0x35053bce,0xb61f3b64,0x3b99b303,
0xbbeab564,0xa6483b99,0xb0b23b88,0x3bff3505,0x3bc3aa48,0xb848bbb6,0xb3c6bbfe,0xbac23444,0xba6d36d7,0x3b50393a,0x38c43b3b,0x367cba0f,
0x381db9ed,0xbbe2afd6,0xbaddb95f,0x31793bf1,0x3bf634a5,0xb303bbb6,0xae46bba8,0xbbceb444,0xb913378b,0x3b773a0f,0x3a2f3b0e,0x35c2b93a,
0xae46bba8,0xba8a2fd6,0xbbf6b4a5,0x389b3bf1,0x3a2f3b0e,0xa648bb25,0x3913b78b,0xbbffb732,0xbb88b3c6,0x37323bce,0x35643bc3,0x3b253303,
0x2a48ba6d,0xbbb6b67c,0xbbfeb8c4,0x34443b50,0x3b3b3add,0xacb5ba8a,0x36d7b81d,0xbbfab89b,0xb9ed30b2,0x3bf139cb,0x395f3bea,0x2fd6b984,
0x3aa7323e,0xb93abbe2,0xb872bbd9,0xba0fb179,0x38723bd9,0x38eca648,0x3aa7323e,0xba4fbbff,0xbaa7b23e,0x3b253bce,0x38723bd9,0x3732b303,
0xb872bbd9,0xb444367c,0xbaa7b23e,0x3bb63b50,0xb95fb0b2,0x3a8a3bf1,0x39ed3bea,0x389b2fd6,0xbb88bbc3,0xa6483732,0xb56433c6,0x3bff3b25,
0xaa48b8c4,0xbac2b7e3,0xbbfeba6d,0x38483af6,0x3b3b381d,0xbb50bbfa,0xb6d7badd,0xb67c2cb5,0x378b2e46,0xbb77bbfa,0xbb0ebbf6,0xb5c2acb5,
0x3ba83a2f,0xb89bba4f,0xb4a5b913,0xba8ab8ec,0x3b0e3bf6,0xa648b505,0x378b2e46,0xbbffbb99,0x34a53913,0x38483444,0x3ba83a2f,0xbac2bbb6,
0xb3c6aa48,0x3bf13bff,0x3bc33bfe,0x2fd62648,0xb8c4b6d7,0x3b993bce,0x3a6d3b3b,0x35053303,0xbaddb9ed,0x3af63b50,0x381d395f,0x37e3367c,
0xbbeabb88,0x3a0f3a8a,0x30b23564,0x393a389b,0x3c003c00,0x2fd62648,0,0x3bf13bff,0x3c003c00,0x35053303,0,0x3b993bce,
0x3c003c00,0x37e3367c,0,0x3af63b50,0x3c003c00,0x393a389b,0,0x3a0f3a8a,0xbbc3bbfe,0xb5c2acb5,0x33c62a48,0xbb77bbfa,
0xba6dbb3b,0xba8ab8ec,0x38c436d7,0xb89bba4f,0xb81db95f,0xbbffbb99,0x3add39ed,0xa648b505,0xb0b2b564,0xbac2bbb6,0x3bea3b88,0x38483444,
0x3b0e3bf6,0x389b2fd6,0xb78bae46,0x3a8a3bf1,0x34a53913,0x3bff3b25,0xbba8ba2f,0xa6483732,0xb78bae46,0x38483af6,0xbb0ebbf6,0xbac2b7e3,
0xbba8ba2f,0xb67c2cb5,0xb4a5b913,0xbb50bbfa,0xb9edbbea,0xba0fb179,0x395f30b2,0xb93abbe2,0x3564b3c6,0xba4fbbff,0x3b883bc3,0x38eca648,
0x3bfe3a6d,0x3732b303,0x2a4838c4,0x3b253bce,0x36d73add,0x3bb63b50,0xbb3bb81d,0xb444367c,0x38723bd9,0x3b253303,0xbaa7b23e,0x37323bce,
0xbaa7b23e,0x34443b50,0xb872bbd9,0xbbb6b67c,0xb872bbd9,0xbbfab89b,0x3aa7323e,0xacb5ba8a,0x3aa7323e,0x2fd6b984,0x38723bd9,0x3bf139cb,
0xb564bbc3,0xbbceb444,0x3b8833c6,0xb303bbb6,0x3bfe38c4,0x35c2b93a,0xaa483a6d,0x3b773a0f,0xb6d7381d,0x389b3bf1,0xbb3bbadd,0xba8a2fd6,
0xb95fbbea,0xbbffb732,0x39edb0b2,0xa648bb25,0x2e463ba8,0x3bff3505,0xbbf6b4a5,0xa6483b99,0xba2fbb0e,0xbac23444,0x3913b78b,0xb848bbb6,
0x3bf634a5,0x367cba0f,0x2e463ba8,0x3b50393a,0xb913378b,0x31793bf1,0xba2fbb0e,0xbbe2afd6,0x30b2bb88,0xbbb6b5c2,0x3bea3564,0x3444bb77,
0x33c63bfe,0x3bfa3179,0xbbc32a48,0xacb53be2,0xb8c4bb3b,0xbbf12648,0x3a6db6d7,0xafd6bbff,0x3add395f,0x3b99b303,0xb81d39ed,0x35053bce,
0xb61f3b64,0x3af6367c,0xbb64b61f,0xb7e33b50,0x361fbb64,0xba0fb89b,0x3b64361f,0x393aba8a,0xb61f3b64,0x38ec39cb,0xbb64b61f,0xba4f3984,
0x361fbb64,0xb732bac2,0x3b64361f,0x3b25b848,0x38c4bb3b,0xb9cbb732,0x3a6d36d7,0x3984bb25,0xbadd395f,0x33033af6,0xb81db9ed,0xbbce37e3,
0x3beab564,0x35c2bbfa,0x30b23b88,0x3b772cb5,0xbbc3aa48,0xba8a3a4f,0x33c6bbfe,0xb89bb8ec,0xba2f3b0e,0x384837e3,0xb913b78b,0xbac23af6,
0x3bf6b4a5,0x367cbbfa,0xae463ba8,0x3b50acb5,0xb913b78b,0xbbe238ec,0x3a2fbb0e,0xb179ba4f,0xae463ba8,0x39843505,0xbbf634a5,0xb9cb3b99,
0x3b3bbadd,0xb505b848,0x36d7381d,0x3b99bac2,0xb9edb0b2,0xbaf63b77,0x395fbbea,0xb7e3b5c2,0xb5643bc3,0x393a3179,0xbb8833c6,0xba0f3be2,
0x3bfeb8c4,0x38ecbbff,0x2a483a6d,0x3a4fa648,0xbbd93aa7,0x2cb5389b,0xb23eb872,0xbbfa3a8a,0x323e3872,0x3bf1b984,0xbbd93aa7,0xafd639cb,
0x3bd9baa7,0x3505bac2,0x323e3872,0x3b99b848,0xb23eb872,0xbaf635c2,0x3bd9baa7,0x37e3bb77,0x3bfeba6d,0x3179b8ec,0xaa4838c4,0x3be2ba4f,
0x36d7badd,0xb9cb3505,0x3b3bb81d,0x3984bb99,0xb95f30b2,0xbbce3bb6,0x39edbbea,0xb303b444,0xbb883bc3,0xb5c23a0f,0xb564b3c6,0xbb77393a,
0xbba83a2f,0xb67c393a,0x34a5b913,0xbb503a0f,0xbb0e3bf6,0x31792fd6,0xb78b2e46,0xbbe23bf1,0xb4a53913,0x3984b732,0xbba83a2f,0xb9cb3b25,
0x378bae46,0x3bcebaf6,0xbb0e3bf6,0xb30337e3,0x3addb9ed,0x38ecb984,0xb81d395f,0x3a4fb9cb,0x3beabb88,0x3732b848,0xb0b23564,0x3b25bac2,
0x3bc3bbfe,0x3444b5c2,0x33c6aa48,0x3bb6bb77,0x3a6dbb3b,0x2cb5b179,0x38c4b6d7,0x3bfabbe2,0xb9a839a8,0xba4f39cb,0x39a8b9a8,0xb8ec3984,
0xb9a839a8,0xbb253ac2,0x39a8b9a8,0xb7323848,0xb9a839a8,0xbbb63b77,0x39a8b9a8,0xb44435c2,0xb9a839a8,0xbbfa3be2,0x39a8b9a8,0xacb53179,
0x381db95f,0x3b50ba0f,0xbadd39ed,0x367cb93a,0x30b2b564,0x3be2bbf1,0xbbea3b88,0xb179afd6,0xb3c62a48,0x39cbbb25,0xbbc33bfe,0xb9843732,
0xb8c436d7,0x3303b7e3,0xba6d3b3b,0xbbce3af6,0xb4a53913,0xbbe23a4f,0x3ba8ba2f,0xb17938ec,0x378bae46,0xb9843b99,0x3b0ebbf6,0x39cbb505,
0x3ba8ba2f,0x33033444,0x34a5b913,0x3bcebbb6,0x3b0ebbf6,0x3b77b93a,0xb78b2e46,0x35c2ba0f,0x2a48b8c4,0x3bfaba8a,0xbbfe3a6d,0xacb5b89b,
0xbb3b381d,0x2fd6b9cb,0xb6d73add,0xbbf13984,0xb9ed3bea,0xbb993848,0x395fb0b2,0xb5053ac2,0x356433c6,0xb7e33b77,0x3b88bbc3,0x3af6b5c2,
0x323e3872,0xbb993ac2,0x3bd9baa7,0x35053848,0x3bd9baa7,0x37e335c2,0xb23eb872,0x3af6bb77,0xb23eb872,0x3a0fbbe2,0xbbd93aa7,0xb93ab179,
0xbbd93aa7,0xba4f2648,0x323e3872,0xb8ec3bff,0xb6d7b81d,0x3ac2baf6,0xbb3b3add,0xb848b7e3,0xb95f3bea,0xbb502cb5,0x39ed30b2,0xb67c3bfa,
0x3b88b3c6,0x31793a4f,0x3564bbc3,0x3be2b8ec,0xaa48ba6d,0x39cbbb99,0xbbfe38c4,0xb984b505,0x3913378b,0xb9843b25,0x3a2fbb0e,0x39cb3732,
0x2e46bba8,0x3bceb7e3,0xbbf634a5,0xb303baf6,0xba2f3b0e,0xbb77acb5,0x3913378b,0xb5c23bfa,0x3bf6b4a5,0x389b38ec,0x2e46bba8,0x3a8aba4f,
0xba6db6d7,0x37e3bb50,0xb8c43b3b,0xbaf6b67c,0x381d39ed,0xb93a3a8a,0x3addb95f,0x3a0f389b,0xb0b2bb88,0x3a4fb984,0xbbea3564,0xb8ecb9cb,
0xb3c63bfe,0xbb253848,0x3bc32a48,0x37323ac2,0x3b64361f,0xb4443b77,0x361fbb64,0x3bb635c2,0xbb64b61f,0x2cb5bbe2,0xb61f3b64,0xbbfab179,
0x3b64361f,0x2fd63bff,0x361fbb64,0x3bf1a648,0xbb64b61f,0xb505bbce,0xb61f3b64,0xbb993303,0xbbeab564,0x2648bb99,0xb0b23b88,0xbbffb505,
0x3bc3aa48,0x38483bb6,0xb3c6bbfe,0x3ac2b444,0xba6d36d7,0xbb50b93a,0x38c43b3b,0xb67c3a0f,0x381db9ed,0x3be22fd6,0xbaddb95f,0xb179bbf1,
0x3bf634a5,0x33033bb6,0xae46bba8,0x3bce3444,0xb913378b,0xbb77ba0f,0x3a2f3b0e,0xb5c2393a,0xae46bba8,0x3a8aafd6,0xbbf6b4a5,0xb89bbbf1,
0x3a2f3b0e,0x26483b25,0x3913b78b,0x3bff3732,0xbb88b3c6,0xb732bbce,0x35643bc3,0xbb25b303,0x2a48ba6d,0x3bb6367c,0xbbfeb8c4,0xb444bb50,
0x3b3b3add,0x2cb53a8a,0x36d7b81d,0x3bfa389b,0xb9ed30b2,0xbbf1b9cb,0x395f3bea,0xafd63984,0x3aa7323e,0x393a3be2,0xb872bbd9,0x3a0f3179,
0x38723bd9,0xb8ec2648,0x3aa7323e,0x3a4f3bff,0xbaa7b23e,0xbb25bbce,0x38723bd9,0xb7323303,0xb872bbd9,0x3444b67c,0xbaa7b23e,0xbbb6bb50,
0xb95fb0b2,0xba8abbf1,0x39ed3bea,0xb89bafd6,0xbb88bbc3,0x2648b732,0xb56433c6,0xbbffbb25,0xaa48b8c4,0x3ac237e3,0xbbfeba6d,0xb848baf6,
0x3b3b381d,0x3b503bfa,0xb6d7badd,0x367cacb5,0x378b2e46,0x3b773bfa,0xbb0ebbf6,0x35c22cb5,0x3ba83a2f,0x389b3a4f,0xb4a5b913,0x3a8a38ec,
0x3b0e3bf6,0x26483505,0x378b2e46,0x3bff3b99,0x34a53913,0xb848b444,0x3ba83a2f,0x3ac23bb6,0xb3c6aa48,0xbbf1bbff,0x3bc33bfe,0xafd6a648,
0xb8c4b6d7,0xbb99bbce,0x3a6d3b3b,0xb505b303,0xbaddb9ed,0xbaf6bb50,0x381d395f,0xb7e3b67c,0xbbeabb88,0xba0fba8a,0x30b23564,0xb93ab89b,
0x3c003c00,0xba4fb9cb,0,0xb8ecb984,0x3c003c00,0xbb25bac2,0,0xb732b848,0x3c003c00,0xbbb6bb77,0,0xb444b5c2,
0x3c003c00,0xbbfabbe2,0,0xacb5b179,0x33c62a48,0x367c393a,0x3bc33bfe,0xbb50ba0f,0x38c436d7,0xb1792fd6,0x3a6d3b3b,0xbbe2bbf1,
0x3add39ed,0xb984b732,0x381d395f,0xb9cbbb25,0x3bea3b88,0xbbcebaf6,0x30b23564,0xb303b7e3,0xbb0ebbf6,0x3be23a4f,0x378b2e46,0x317938ec,
0xb4a5b913,0x39843b99,0x3ba83a2f,0xb9cbb505,0x378b2e46,0xb3033444,0x3b0e3bf6,0xbbcebbb6,0x3ba83a2f,0xbb77b93a,0x34a53913,0xb5c2ba0f,
0xb95fb0b2,0x2cb5b89b,0xb9edbbea,0x3bfa3a8a,0xbb88bbc3,0x3bf13984,0x3564b3c6,0x2fd639cb,0xaa48b8c4,0x35053ac2,0x3bfe3a6d,0xbb99b848,
0x3b3b381d,0xbaf6b5c2,0x36d73add,0xb7e3bb77,0x38723bd9,0xbb99bac2,0xbaa7b23e,0x3505b848,0xbaa7b23e,0x37e3b5c2,0xb872bbd9,0x3af63b77,
0xb872bbd9,0x3a0f3be2,0x3aa7323e,0xb93a3179,0x3aa7323e,0xba4fa648,0x38723bd9,0xb8ecbbff,0x3b8833c6,0xb84837e3,0x35643bc3,0xbac2baf6,
0xaa483a6d,0xb67cbbfa,0xbbfeb8c4,0x3b502cb5,0xbb3bbadd,0x3be238ec,0x36d7b81d,0xb1793a4f,0x39edb0b2,0xb9843505,0x395f3bea,0xb9cbbb99,
0xae46bba8,0x39843b25,0x3bf634a5,0xb9cb3732,0x3a2f3b0e,0xbbceb7e3,0xb913378b,0x3303baf6,0xbbf6b4a5,0x3b77acb5,0xae46bba8,0x35c23bfa,
0x3913b78b,0xb89b38ec,0x3a2f3b0e,0xba8aba4f,0xbbeab564,0x3af6b67c,0x30b2bb88,0x37e33b50,0x3bc3aa48,0xba0f389b,0x33c63bfe,0xb93aba8a,
0xba6d36d7,0x38ecb9cb,0xb8c4bb3b,0x3a4f3984,0x381db9ed,0xb7323ac2,0x3add395f,0xbb25b848,0xb61f3b64,0xb444bb77,0xbb64b61f,0x3bb6b5c2,
0x361fbb64,0x2cb53be2,0x3b64361f,0xbbfa3179,0xb61f3b64,0x2fd6bbff,0xbb64b61f,0x3bf12648,0x361fbb64,0xb5053bce,0x3b64361f,0xbb99b303,
0x3a6d36d7,0xbbff3505,0xb8c43b3b,0xa648bb99,0xb81db9ed,0x3ac23444,0x3addb95f,0xb8483bb6,0x30b23b88,0xb67cba0f,0xbbea3564,0x3b50b93a,
0x33c6bbfe,0xb1793bf1,0x3bc32a48,0xbbe22fd6,0x3a2fbb0e,0xb3033bb6,0x3913378b,0xbbce3444,0xbbf634a5,0x3b77ba0f,0x2e46bba8,0x35c2393a,
0x3913378b,0xba8aafd6,0xba2f3b0e,0x389bbbf1,0x2e46bba8,0xa6483b25,0x3bf6b4a5,0xbbff3732,0xb6d7b81d,0x3b25b303,0x3b3bbadd,0xb7323bce,
0xb95f3bea,0x3444bb50,0xb9edb0b2,0x3bb6b67c,0x3b88b3c6,0xbbfa389b,0xb5643bc3,0x2cb5ba8a,0xaa48ba6d,0x2fd63984,0x3bfeb8c4,0xbbf139cb,
0xbbd93aa7,0x393abbe2,0xb23eb872,0x3a0fb179,0x323e3872,0xb8eca648,0xbbd93aa7,0x3a4fbbff,0x3bd9baa7,0xbb253bce,0x323e3872,0xb732b303,
0xb23eb872,0x3444367c,0x3bd9baa7,0xbbb63b50,0xaa4838c4,0xb89b2fd6,0xbbfe3a6d,0x3a8abbf1,0x3b3bb81d,0xbbff3b25,0xb6d73add,0xa648b732,
0x39edbbea,0xb8483af6,0x395fb0b2,0xbac237e3,0xb564b3c6,0x367c2cb5,0x3b88bbc3,0xbb503bfa,0x3ba8ba2f,0xbb773bfa,0xb4a53913,0xb5c22cb5,
0x3b0ebbf6,0xb89b3a4f,0x378bae46,0xba8a38ec,0x34a5b913,0xa6483505,0x3ba8ba2f,0xbbff3b99,0xb78b2e46,0x3848b444,0x3b0ebbf6,0xbac23bb6,
0x381db95f,0x2fd6a648,0x3addb9ed,0xbbf13bff,0x30b2b564,0x3505b303,0x3beabb88,0xbb993bce,0xb3c62a48,0x37e3b67c,0x3bc3bbfe,0xbaf63b50,
0xb8c436d7,0x393ab89b,0x3a6dbb3b,0xba0f3a8a,0xb9a839a8,0x3bf1bbff,0x39a8b9a8,0xafd62648,0xb9a839a8,0x3b99bbce,0x39a8b9a8,0xb5053303,
0xb9a839a8,0x3af6bb50,0x39a8b9a8,0xb7e3367c,0xb9a839a8,0x3a0fba8a,0x39a8b9a8,0xb93a389b,0xbadd39ed,0x35c2acb5,0xb81d395f,0x3b77bbfa,
0xbbea3b88,0x3a8ab8ec,0xb0b23564,0x389bba4f,0xbbc33bfe,0x3bffbb99,0x33c6aa48,0x2648b505,0xba6d3b3b,0x3ac2bbb6,0x38c4b6d7,0xb8483444,
0x34a5b913,0xba8a3bf1,0xbba83a2f,0x389bafd6,0xb78b2e46,0x26483732,0xbb0e3bf6,0x3bffbb25,0xbba83a2f,0x3ac2b7e3,0xb4a53913,0x3848baf6,
0xbb0e3bf6,0x3b50bbfa,0x378bae46,0xb67cacb5,0x3bfeba6d,0xba0f3179,0x2a48b8c4,0xb93a3be2,0x36d7badd,0xba4f3bff,0xbb3b381d,0x38ec2648,
0xb95f30b2,0x37323303,0xb9ed3bea,0x3b25bbce,0xbb883bc3,0x3bb6bb50,0x356433c6,0xb444b67c,0x323e3872,0x3732bbce,0x3bd9baa7,0xbb253303,
0x3bd9baa7,0xbbb6367c,0xb23eb872,0xb4443b50,0xb23eb872,0xacb53a8a,0xbbd93aa7,0x3bfab89b,0xbbd93aa7,0x3bf1b9cb,0x323e3872,0xafd6b984,
0xbb3b3add,0x3bceb444,0x36d7381d,0x3303bbb6,0x39ed30b2,0xb5c2b93a,0x395fbbea,0xbb773a0f,0x3564bbc3,0xb89b3bf1,0xbb8833c6,0x3a8a2fd6,
0xbbfe38c4,0x3bffb732,0x2a483a6d,0x2648bb25,0xb913b78b,0x26483b99,0xba2f3b0e,0x3bffb505,0xae463ba8,0x3848bbb6,0x3bf6b4a5,0xbac2b444,
0x3a2fbb0e,0xbb50393a,0xb913b78b,0x367c3a0f,0xbbf634a5,0x3be2afd6,0xae463ba8,0x3179bbf1,0x38c4bb3b,0xbbb635c2,0xba6db6d7,0x34443b77,
0xbadd395f,0x3bfab179,0x381d39ed,0xacb5bbe2,0x3beab564,0xbbf1a648,0xb0b2bb88,0xafd63bff,0xbbc3aa48,0x3b993303,0xb3c63bfe,0x3505bbce,
0x3b64361f,0xb7e3bb50,0x361fbb64,0xbaf6367c,0xbb64b61f,0x393a3a8a,0xb61f3b64,0x3a0fb89b,0x3b64361f,0xba4fb984,0x361fbb64,0xb8ec39cb,
0xbb64b61f,0x3b253848,0xb61f3b64,0x3732bac2,0xb0b23b88,0x39cbb732,0x3bea3564,0xb984bb25,0xb3c6bbfe,0xb3033af6,0xbbc32a48,0x3bce37e3,
0x38c43b3b,0xb5c2bbfa,0x3a6db6d7,0xbb772cb5,0xbaddb95f,0x3a8a3a4f,0xb81d39ed,0x389bb8ec,0xbbf6b4a5,0x3ac23af6,0x2e463ba8,0x3848b7e3,
0x3913b78b,0xbb50acb5,0xba2fbb0e,0x367c3bfa,0x2e463ba8,0x3179ba4f,0x3bf634a5,0xbbe2b8ec,0xba2fbb0e,0x39cb3b99,0xb913378b,0x3984b505,
0xb564bbc3,0xb5053848,0xbb88b3c6,0x3b993ac2,0x3bfe38c4,0xbaf6bb77,0x2a48ba6d,0xb7e335c2,0xb6d7381d,0x393ab179,0x3b3b3add,0xba0fbbe2,
0xb95fbbea,0x38ec3bff,0xb9ed30b2,0x3a4f2648,0x3aa7323e,0xbbfaba8a,0xb872bbd9,0xacb5389b,0x38723bd9,0xafd6b9cb,0x3aa7323e,0xbbf1b984,
0xbaa7b23e,0x3b993848,0x38723bd9,0xb505bac2,0xb872bbd9,0x37e33b77,0xbaa7b23e,0x3af635c2,0x39ed3bea,0xb179b8ec,0x395f30b2,0xbbe2ba4f,
0xb56433c6,0x39cb3505,0x3b883bc3,0xb984bb99,0xbbfeba6d,0x3bce3bb6,0x2a4838c4,0x3303b444,0xb6d7badd,0x35c23a0f,0xbb3bb81d,0x3b77393a,
0xb78bae46,0x3b503a0f,0x3b0e3bf6,0xb67cb93a,0xbba8ba2f,0x3be23bf1,0x34a53913,0x3179afd6,0xbb0ebbf6,0x39cb3b25,0xb78bae46,0x39843732,
0xb4a5b913,0x330337e3,0xbba8ba2f,0x3bce3af6,0xbbc3bbfe,0x38ec3984,0xb3c6aa48,0x3a4f39cb,0xba6dbb3b,0x37323848,0xb8c4b6d7,0x3b253ac2,
0xb81db95f,0x344435c2,0xbaddb9ed,0x3bb63b77,0xb0b2b564,0x2cb53179,0xbbeabb88,0x3bfa3be2,0x3c003c00,0x3a4f39cb,0,0x38ec3984,
0x3c003c00,0x3b253ac2,0,0x37323848,0x3c003c00,0x3bb63b77,0,0x344435c2,0x3c003c00,0x3bfa3be2,0,0x2cb53179,
0x33c62a48,0xb67cb93a,0x3bc33bfe,0x3b503a0f,0x38c436d7,0x3179afd6,0x3a6d3b3b,0x3be23bf1,0x3add39ed,0x39843732,0x381d395f,0x39cb3b25,
0x3bea3b88,0x3bce3af6,0x30b23564,0x330337e3,0xbb0ebbf6,0xbbe2ba4f,0x378b2e46,0xb179b8ec,0xb4a5b913,0xb984bb99,0x3ba83a2f,0x39cb3505,
0x378b2e46,0x3303b444,0x3b0e3bf6,0x3bce3bb6,0x3ba83a2f,0x3b77393a,0x34a53913,0x35c23a0f,0xb95fb0b2,0xacb5389b,0xb9edbbea,0xbbfaba8a,
0xbb88bbc3,0xbbf1b984,0x3564b3c6,0xafd6b9cb,0xaa48b8c4,0xb505bac2,0x3bfe3a6d,0x3b993848,0x3b3b381d,0x3af635c2,0x36d73add,0x37e33b77,
0x38723bd9,0x3b993ac2,0xbaa7b23e,0xb5053848,0xbaa7b23e,0xb7e335c2,0xb872bbd9,0xbaf6bb77,0xb872bbd9,0xba0fbbe2,0x3aa7323e,0x393ab179,
0x3aa7323e,0x3a4f2648,0x38723bd9,0x38ec3bff,0x3b8833c6,0x3848b7e3,0x35643bc3,0x3ac23af6,0xaa483a6d,0x367c3bfa,0xbbfeb8c4,0xbb50acb5,
0xbb3bbadd,0xbbe2b8ec,0x36d7b81d,0x3179ba4f,0x39edb0b2,0x3984b505,0x395f3bea,0x39cb3b99,0xae46bba8,0xb984bb25,0x3bf634a5,0x39cbb732,
0x3a2f3b0e,0x3bce37e3,0xb913378b,0xb3033af6,0xbbf6b4a5,0xbb772cb5,0xae46bba8,0xb5c2bbfa,0x3913b78b,0x389bb8ec,0x3a2f3b0e,0x3a8a3a4f,
0xbbeab564,0xbaf6367c,0x30b2bb88,0xb7e3bb50,0x3bc3aa48,0x3a0fb89b,0x33c63bfe,0x393a3a8a,0xba6d36d7,0xb8ec39cb,0xb8c4bb3b,0xba4fb984,
0x381db9ed,0x3732bac2,0x3add395f,0x3b253848,0xb61f3b64,0x34443b77,0xbb64b61f,0xbbb635c2,0x361fbb64,0xacb5bbe2,0x3b64361f,0x3bfab179,
0xb61f3b64,0xafd63bff,0xbb64b61f,0xbbf1a648,0x361fbb64,0x3505bbce,0x3b64361f,0x3b993303,0x3a6d36d7,0x3bffb505,0xb8c43b3b,0x26483b99,
0xb81db9ed,0xbac2b444,0x3addb95f,0x3848bbb6,0x30b23b88,0x367c3a0f,0xbbea3564,0xbb50393a,0x33c6bbfe,0x3179bbf1,0x3bc32a48,0x3be2afd6,
0x3a2fbb0e,0x3303bbb6,0x3913378b,0x3bceb444,0xbbf634a5,0xbb773a0f,0x2e46bba8,0xb5c2b93a,0x3913378b,0x3a8a2fd6,0xba2f3b0e,0xb89b3bf1,
0x2e46bba8,0x2648bb25,0x3bf6b4a5,0x3bffb732,0xb6d7b81d,0xbb253303,0x3b3bbadd,0x3732bbce,0xb95f3bea,0xb4443b50,0xb9edb0b2,0xbbb6367c,
0x3b88b3c6,0x3bfab89b,0xb5643bc3,0xacb53a8a,0xaa48ba6d,0xafd6b984,0x3bfeb8c4,0x3bf1b9cb,0xbbd93aa7,0xb93a3be2,0xb23eb872,0xba0f3179,
0x323e3872,0x38ec2648,0xbbd93aa7,0xba4f3bff,0x3bd9baa7,0x3b25bbce,0x323e3872,0x37323303,0xb23eb872,0xb444b67c,0x3bd9baa7,0x3bb6bb50,
0xaa4838c4,0x389bafd6,0xbbfe3a6d,0xba8a3bf1,0x3b3bb81d,0x3bffbb25,0xb6d73add,0x26483732,0x39edbbea,0x3848baf6,0x395fb0b2,0x3ac2b7e3,
0xb564b3c6,0xb67cacb5,0x3b88bbc3,0x3b50bbfa,0x3ba8ba2f,0x3b77bbfa,0xb4a53913,0x35c2acb5,0x3b0ebbf6,0x389bba4f,0x378bae46,0x3a8ab8ec,
0x34a5b913,0x2648b505,0x3ba8ba2f,0x3bffbb99,0xb78b2e46,0xb8483444,0x3b0ebbf6,0x3ac2bbb6,0x381db95f,0xafd62648,0x3addb9ed,0x3bf1bbff,
0x30b2b564,0xb5053303,0x3beabb88,0x3b99bbce,0xb3c62a48,0xb7e3367c,0x3bc3bbfe,0x3af6bb50,0xb8c436d7,0xb93a389b,0x3a6dbb3b,0x3a0fba8a,
0xb9a839a8,0xbbf13bff,0x39a8b9a8,0x2fd6a648,0xb9a839a8,0xbb993bce,0x39a8b9a8,0x3505b303,0xb9a839a8,0xbaf63b50,0x39a8b9a8,0x37e3b67c,
0xb9a839a8,0xba0f3a8a,0x39a8b9a8,0x393ab89b,0xbadd39ed,0xb5c22cb5,0xb81d395f,0xbb773bfa,0xbbea3b88,0xba8a38ec,0xb0b23564,0xb89b3a4f,
0xbbc33bfe,0xbbff3b99,0x33c6aa48,0xa6483505,0xba6d3b3b,0xbac23bb6,0x38c4b6d7,0x3848b444,0x34a5b913,0x3a8abbf1,0xbba83a2f,0xb89b2fd6,
0xb78b2e46,0xa648b732,0xbb0e3bf6,0xbbff3b25,0xbba83a2f,0xbac237e3,0xb4a53913,0xb8483af6,0xbb0e3bf6,0xbb503bfa,0x378bae46,0x367c2cb5,
0x3bfeba6d,0x3a0fb179,0x2a48b8c4,0x393abbe2,0x36d7badd,0x3a4fbbff,0xbb3b381d,0xb8eca648,0xb95f30b2,0xb732b303,0xb9ed3bea,0xbb253bce,
0xbb883bc3,0xbbb63b50,0x356433c6,0x3444367c,0x323e3872,0xb7323bce,0x3bd9baa7,0x3b25b303,0x3bd9baa7,0x3bb6b67c,0xb23eb872,0x3444bb50,
0xb23eb872,0x2cb5ba8a,0xbbd93aa7,0xbbfa389b,0xbbd93aa7,0xbbf139cb,0x323e3872,0x2fd63984,0xbb3b3add,0xbbce3444,0x36d7381d,0xb3033bb6,
0x39ed30b2,0x35c2393a,0x395fbbea,0x3b77ba0f,0x3564bbc3,0x389bbbf1,0xbb8833c6,0xba8aafd6,0xbbfe38c4,0xbbff3732,0x2a483a6d,0xa6483b25,
0xb913b78b,0xa648bb99,0xba2f3b0e,0xbbff3505,0xae463ba8,0xb8483bb6,0x3bf6b4a5,0x3ac23444,0x3a2fbb0e,0x3b50b93a,0xb913b78b,0xb67cba0f,
0xbbf634a5,0xbbe22fd6,0xae463ba8,0xb1793bf1,0x38c4bb3b,0x3bb6b5c2,0xba6db6d7,0xb444bb77,0xbadd395f,0xbbfa3179,0x381d39ed,0x2cb53be2,
0x3beab564,0x3bf12648,0xb0b2bb88,0x2fd6bbff,0xbbc3aa48,0xbb99b303,0xb3c63bfe,0xb5053bce,0x3b64361f,0x37e33b50,0x361fbb64,0x3af6b67c,
0xbb64b61f,0xb93aba8a,0xb61f3b64,0xba0f389b,0x3b64361f,0x3a4f3984,0x361fbb64,0x38ecb9cb,0xbb64b61f,0xbb25b848,0xb61f3b64,0xb7323ac2,
0xb0b23b88,0xb9cb3732,0x3bea3564,0x39843b25,0xb3c6bbfe,0x3303baf6,0xbbc32a48,0xbbceb7e3,0x38c43b3b,0x35c23bfa,0x3a6db6d7,0x3b77acb5,
0xbaddb95f,0xba8aba4f,0xb81d39ed,0xb89b38ec,0xbbf6b4a5,0xbac2baf6,0x2e463ba8,0xb84837e3,0x3913b78b,0x3b502cb5,0xba2fbb0e,0xb67cbbfa,
0x2e463ba8,0xb1793a4f,0x3bf634a5,0x3be238ec,0xba2fbb0e,0xb9cbbb99,0xb913378b,0xb9843505,0xb564bbc3,0x3505b848,0xbb88b3c6,0xbb99bac2,
0x3bfe38c4,0x3af63b77,0x2a48ba6d,0x37e3b5c2,0xb6d7381d,0xb93a3179,0x3b3b3add,0x3a0f3be2,0xb95fbbea,0xb8ecbbff,0xb9ed30b2,0xba4fa648,
0x3aa7323e,0x3bfa3a8a,0xb872bbd9,0x2cb5b89b,0x38723bd9,0x2fd639cb,0x3aa7323e,0x3bf13984,0xbaa7b23e,0xbb99b848,0x38723bd9,0x35053ac2,
0xb872bbd9,0xb7e3bb77,0xbaa7b23e,0xbaf6b5c2,0x39ed3bea,0x317938ec,0x395f30b2,0x3be23a4f,0xb56433c6,0xb9cbb505,0x3b883bc3,0x39843b99,
0xbbfeba6d,0xbbcebbb6,0x2a4838c4,0xb3033444,0xb6d7badd,0xb5c2ba0f,0xbb3bb81d,0xbb77b93a,0xb78bae46,0xbb50ba0f,0x3b0e3bf6,0x367c393a,
0xbba8ba2f,0xbbe2bbf1,0x34a53913,0xb1792fd6,0xbb0ebbf6,0xb9cbbb25,0xb78bae46,0xb984b732,0xb4a5b913,0xb303b7e3,0xbba8ba2f,0xbbcebaf6,
0xbbc3bbfe,0xb8ecb984,0xb3c6aa48,0xba4fb9cb,0xba6dbb3b,0xb732b848,0xb8c4b6d7,0xbb25bac2,0xb81db95f,0xb444b5c2,0xbaddb9ed,0xbbb6bb77,
0xb0b2b564,0xacb5b179,0xbbeabb88,0xbbfabbe2,0x3c003c00,0x96480000,0x3c003c00,0xa311a248,0x3c003c00,0x9cb69a48,0x3c003c00,0xa452a3db,
0x3c003c00,0x9fdb9e48,0x3c003c00,0xa51ba4b6,0x3c003c00,0xa17fa0b6,0x3bff3c00,0xa5e4a57f,0x3c003c00,0x9fdb0000,0x3bfb3bfc,0xac6aabd9,
0x3bff3c00,0xa5e4a3db,0x3bf93bfa,0xad65ace7,0x3bfe3bff,0xa8e8a7da,0x3bf63bf7,0xae5fade2,0x3bfd3bfe,0xaadea9e3,0x3bf23bf4,0xaf59aedc,
0x3c003c00,0xa3110000,0x3bf03bf4,0xafefaf0e,0x3bfe3bff,0xa94da711,0x3be83bed,0xb0d7b067,0x3bfb3bfd,0xac6aab11,0x3bdf3be4,0xb1b6b147,
0x3bf63bf9,0xae2dad4c,0x3bd43bda,0xb294b226,0x3c003c00,0xa51b0000,0x3bdf3be6,0xb1b6b115,0x3bfc3bfe,0xaba7a91b,0x3bcf3bd7,0xb2f7b257,
0x3bf63bf9,0xae5fad1a,0x3bbc3bc6,0xb41ab396,0x3bec3bf1,0xb074afa4,0x3ba53bb1,0xb4b7b469,0x3bff3c00,0xa6ad0000,0x3bc83bd4,0xb371b2a1,
0x3bfa3bfd,0xad00aaac,0x3bac3bbb,0xb487b420,0x3bef3bf5,0xb029aeaa,0x3b8b3b9d,0xb552b4ed,0x3bde3be7,0xb1cfb0fd,0x3b653b79,0xb61ab5b6,
0x3bff3c00,0xa81f0000,0x3bab3bbc,0xb493b414,0x3bf63bfc,0xae2dac1f,0x3b813b97,0xb58db511,0x3be53bef,0xb122b01d,0x3b4f3b69,0xb682b608,
0x3bcc3bda,0xb328b226,0x3b163b33,0xb76fb6f9,0x3bfe3c00,0xa8e80000,0x3b873ba0,0xb56ab4d5,0x3bf23bfa,0xaf59ace7,0x3b4c3b6b,0xb68db5fd,
0x3bda3be8,0xb219b0e4,0x3b073b2b,0xb7a6b71b,0x3bb73bca,0xb43eb34c,0x3ab63ae0,0xb85ab817,0x3bfe3c00,0xa9b10000,0x3b5e3b80,0xb63cb593,
0x3bee3bf8,0xb042adb0,0x3b103b39,0xb785b6e3,0x3bce3be0,0xb30fb1aa,0x3ab33ae3,0xb85fb812,0x3b9e3bb7,0xb4e7b438,0x3a493a7f,0xb8f3b8ab,
0x3bfd3c00,0xaa7a0000,0x3b2f3b5a,0xb70ab64e,0x3be83bf6,0xb0d7ae78,0x3acb3aff,0xb83ab7c2,0x3bbf3bd6,0xb402b26f,0x3a543a92,0xb8e5b891,
0x3b813ba2,0xb58db4c9,0x39cd3a13,0xb982b935,0x3bfd3c00,0xab430000,0x3afb3b30,0xb7d2b705,0x3be23bf3,0xb16caf40,0x3a7e3abf,0xb8adb84d,
0x3bae3bcb,0xb47bb334,0x39eb3a37,0xb962b909,0x3b603b8a,0xb631b558,0x3946399b,0xba04b9b5,0x3bfc3c00,0xac060000,0x3ac13b02,0xb84ab7b7,
0x3bdc3bf0,0xb201b004,0x3a293a78,0xb91bb8b5,0x3b9c3bc0,0xb4f3b3f7,0x397939d4,0xb9d6b97b,0x3b3d3b70,0xb6d2b5e5,0x38b23918,0xba7aba2b,
0x3bfb3c00,0xac6a0000,0x3a813ad0,0xb8a8b832,0x3bd43bed,0xb294b067,0x39cd3a2b,0xb982b918,0x3b873bb2,0xb56ab45d,0x38fd3969,0xba41b9e5,
0x3b163b53,0xb76fb670,0x3815388c,0xbae1ba95,0x3bfa3c00,0xacce0000,0x3a3d3a99,0xb902b887,0x3bcc3be9,0xb328b0cb,0x396b39d8,0xb9e3b976,
0x3b713ba4,0xb5dfb4bd,0x387a38f6,0xbaa2ba47,0x3aeb3b33,0xb805b6f9,0x36dd37ee,0xbb3abaf3,0x3bf93c00,0xad330000,0x39f43a5e,0xb958b8d8,
0x3bc33be5,0xb3bab12e,0x39023980,0xba3db9d0,0x3b593b95,0xb654b51d,0x37dd387c,0xbaf7baa0,0x3abd3b11,0xb850b780,0x358136b5,0xbb83bb43,
0x3bf83c00,0xad970000,0x39a63a1f,0xb9aab927,0x3bba3be1,0xb426b191,0x38943922,0xba90ba23,0x3b3f3b84,0xb6c6b57c,0x36bb37f9,0xbb42baf0,
0x3a8c3aed,0xb899b802,0x341a3570,0xbbbcbb86,0x3bf73c00,0xadfb0000,0x395439dc,0xb9f8b972,0x3bb03bdc,0xb46fb1f4,0x382038bf,0xbadbba71,
0x3b243b72,0xb737b5da,0x358d36ee,0xbb81bb36,0x3a583ac6,0xb8e0b842,0x31533420,0xbbe3bbbb,0x3bf63c00,0xae5f0000,0x38fd3996,0xba41b9ba,
0x3ba53bd7,0xb4b7b257,0x374e3858,0xbb1ebab8,0x3b073b5f,0xb7a6b637,0x345735da,0xbbb3bb72,0x3a213a9c,0xb924b881,0x2cce3191,0xbbfabbe1,
0x3bf53c00,0xaec30000,0x38a3394d,0xba85b9fe,0x3b9a3bd2,0xb4ffb2b9,0x365437d8,0xbb59baf9,0x3ae83b4b,0xb80ab693,0x323234bd,0xbbd9bba4,
0x39e73a71,0xb966b8bf,0xa4522db0,0xbc00bbf8,0x3bf33c00,0xaf270000,0x38453900,0xbac4ba3f,0x3b8e3bcd,0xb546b31b,0x355236f9,0xbb8bbb33,
0x3ac73b36,0xb840b6ee,0x2f593334,0xbbf2bbcb,0x39aa3a43,0xb9a6b8fb,0xaef51a48,0xbbf4bc00,0x3bf23c00,0xaf8b0000,0x37c838b0,0xbafeba7c,
0x3b813bc7,0xb58db37d,0x344b3614,0xbbb5bb67,0x3aa53b20,0xb874b748,0x288430e4,0xbbffbbe8,0x396b3a13,0xb9e3b935,0xb263ad4c,0xbbd7bbf9,
0x3bf03c00,0xafef0000,0x36ff385d,0xbb32bab5,0x3b733bc1,0xb5d4b3df,0x327c3529,0xbbd6bb93,0x3a813b08,0xb8a8b7a1,0xa9b12d1a,0xbbfebbf9,
0x392939e1,0xba1db96d,0xb49fb160,0xbba9bbe3,0x3bef3c00,0xb0290000,0x36313807,0xbb60bae9,0x3b653bbb,0xb61ab420,0x305b3438,0xbbedbbb7,
0x3a5c3af0,0xb8dbb7f9,0xafef1e48,0xbbf0bc00,0x38e539ad,0xba54b9a4,0xb602b408,0xbb6abbbe,0x3bed3c00,0xb05b0000,0x355e375e,0xbb89bb1a,
0x3b573bb4,0xb65fb451,0x2c6a3288,0xbbfbbbd5,0x3a353ad6,0xb90cb828,0xb27cac51,0xbbd6bbfb,0x389e3976,0xba89b9d8,0xb759b558,0xbb1bbb8a,
0x3beb3c00,0xb08d0000,0x348736aa,0xbbacbb46,0x3b473bad,0xb6a4b481,0x16483099,0xbc00bbeb,0x3a0d3abc,0xb93cb852,0xb47bb080,0xbbaebbec,
0x3855393e,0xbababa0b,0xb850b69e,0xbabdbb49,0x3be93c00,0xb0be0000,0x335935f1,0xbbc9bb6e,0x3b373ba6,0xb6e8b4b1,0xac382d4c,0xbbfcbbf9,
0x39e33aa0,0xb96bb87c,0xb5b1b2d2,0xbb7abbd1,0x380a3905,0xbae8ba3b,0xb8eab7d8,0xba50baf9,0x3be73c00,0xb0f00000,0x319e3534,0xbbe0bb91,
0x3b273b9e,0xb72cb4e1,0xb042257f,0xbbeebc00,0x39b83a83,0xb999b8a6,0xb6ddb48d,0xbb3abbab,0x377a38c9,0xbb13ba69,0xb979b881,0xb9d6ba9c,
0x3be53c00,0xb1220000,0x2fbd3475,0xbbf1bbaf,0x3b163b97,0xb76fb511,0xb263a91b,0xbbd7bbfe,0x398b3a65,0xb9c5b8ce,0xb7feb5ab,0xbaeebb7b,
0x36dd388c,0xbb3aba95,0xb9fcb90e,0xb94fba33,0x3be33c00,0xb1530000,0x2c383365,0xbbfcbbc9,0x3b043b8f,0xb7b2b540,0xb43eae78,0xbbb7bbf6,
0x395d3a47,0xb9f0b8f6,0xb889b6c1,0xba97bb41,0x363c384d,0xbb5ebabf,0xba73b992,0xb8bcb9be,0x3be13c00,0xb1850000,0x217f31db,0xbc00bbdd,
0x3af13b86,0xb7f3b570,0xb546b12e,0xbb8ebbe5,0x392e3a27,0xba19b91d,0xb90cb7cd,0xba35bafc,0x3599380d,0xbb7fbae6,0xbadbba0b,0xb820b93e,
0x3bdf3c00,0xb1b60000,0xa9b1304e,0xbbfebbed,0x3ade3b7d,0xb81ab59f,0xb648b31b,0xbb5cbbcd,0x38fd3a07,0xba41b943,0xb986b867,0xb9c9baae,
0x34f33796,0xbb9cbb0b,0xbb35ba78,0xb6f4b8b5,0x3bdd3c00,0xb1e80000,0xae5f2d7e,0xbbf6bbf8,0x3acb3b74,0xb83ab5ce,0xb742b481,0xbb21bbad,
0x38cc39e5,0xba67b969,0xb9f8b8e2,0xb954ba56,0x344b3710,0xbbb5bb2e,0xbb7fbad9,0xb599b822,0x3bda3c00,0xb2190000,0xb0f028b6,0xbbe7bbff,
0x3ab63b6b,0xb85ab5fd,0xb81ab570,0xbadebb86,0x389939c3,0xba8cb98d,0xba60b956,0xb8d6b9f6,0x33403687,0xbbcbbb4e,0xbbb8bb2e,0xb432b710,
0x3bff3bff,0xa6ada648,0x3bfe3bff,0xa8e8a8b6,0x3bff3bff,0xa776a711,0x3bfe3bfe,0xa94da91b,0x3bff3bff,0xa81fa7da,0x3bfe3bfe,0xa9b1a97f,
0x3bff3bff,0xa884a852,0x3bfe3bfe,0xaa16a9e3,0x3bef3bf1,0xb029afd6,0x3bda3bdd,0xb219b1db,0x3bea3bed,0xb0a6b067,0x3bd43bd7,0xb294b257,
0x3be53be8,0xb122b0e4,0x3bce3bd1,0xb30fb2d2,0x3be03be3,0xb19eb160,0x3bc63bca,0xb389b34c,0x3bc83bce,0xb371b303,0x3b873b91,0xb56ab534,
0x3bba3bc1,0xb426b3df,0x3b733b7d,0xb5d4b59f,0x3bab3bb2,0xb493b45d,0x3b5e3b69,0xb63cb608,0x3b9a3ba2,0xb4ffb4c9,0x3b473b53,0xb6a4b670,
0x3b8b3b99,0xb552b505,0x3b073b1a,0xb7a6b75e,0x3b6f3b7d,0xb5ebb59f,0x3ade3af3,0xb81ab7ee,0x3b4f3b5f,0xb682b637,0x3ab33ac9,0xb85fb83d,
0x3b2c3b3e,0xb715b6cc,0x3a853a9c,0xb8a3b881,0x3b3a3b50,0xb6ddb67c,0x3a5c3a7c,0xb8dbb8b0,0x3b0a3b22,0xb79bb73d,0x3a193a3b,0xb92eb905,
0x3ad53af0,0xb82ab7f9,0x39d239f6,0xb97db956,0x3a9b3ab8,0xb884b858,0x398639ad,0xb9c9b9a4,0x3ad53af6,0xb82ab7e3,0x398b39ba,0xb9c5b996,
0x3a8c3ab1,0xb899b862,0x3929395b,0xba1db9f2,0x3a3d3a65,0xb902b8ce,0x38c138f6,0xba6fba47,0x39e73a13,0xb966b935,0x3855388c,0xbababa95,
0x3a5c3a8a,0xb8dbb89b,0x389938d8,0xba8cba5e,0x39f83a2b,0xb954b918,0x38153858,0xbae1bab8,0x398b39c3,0xb9c5b98d,0x371537a1,0xbb2cbb08,
0x39163951,0xba2db9fa,0x35f73687,0xbb6cbb4e,0x39d23a0f,0xb97db93a,0x371537b7,0xbb2cbb02,0x394f3992,0xb9fcb9be,0x35c83670,0xbb76bb53,
0x38c13909,0xba6fba37,0x346f351d,0xbbb0bb95,0x382a3877,0xbad5baa3,0x3219337d,0xbbdabbc7,0x39373984,0xba11b9cb,0x34cf3593,0xbba1bb80,
0x389438e7,0xba90ba52,0x327c3408,0xbbd6bbbe,0x37c8383d,0xbafebac9,0x2e9130e4,0xbbf5bbe8,0x36543710,0xbb59bb2e,0x16482aac,0xbc00bbfd,
0x388e38ec,0xba93ba4f,0x30d732a1,0xbbe8bbd4,0x3790382d,0xbb0dbad3,0x28e82e14,0xbbfebbf7,0x35eb36c1,0xbb6fbb41,0xaccea4b6,0xbbfabc00,
0x34323511,0xbbb8bb97,0xb201b036,0xbbdcbbee,0x37b23848,0xbb04bac2,0x96482bd9,0xbc00bbfc,0x35df36cc,0xbb71bb3e,0xb010ac1f,0xbbefbbfc,
0x33eb34ed,0xbbc0bb9d,0xb402b20d,0xbbbfbbdb,0x2fef31f4,0xbbf0bbdc,0xb5ebb4f9,0xbb6fbb9b,0x36313732,0xbb60bb25,0xb0f0ad7e,0xbbe7bbf8,
0x341a3529,0xbbbcbb93,0xb49fb31b,0xbba9bbcd,0x2fbd320d,0xbbf1bbdb,0xb6afb5ab,0xbb45bb7b,0xa4522aac,0xbc00bbfd,0xb850b7ac,0xbabdbb05,
0x349f35c2,0xbba9bb77,0xb4dbb365,0xbb9fbbc9,0x308d32ea,0xbbebbbd0,0xb715b5fd,0xbb2cbb6b,0x9fdb2c51,0xbc00bbfb,0xb894b812,0xba90bae3,
0xb109ad4c,0xbbe6bbf9,0xb982b90e,0xb9cdba33,0x32013444,0xbbdcbbb6,0xb721b5f1,0xbb2abb6e,0x26ad2edc,0xbbffbbf4,0xb8adb822,0xba7ebad9,
0xb05bab11,0xbbedbbfd,0xb9aab930,0xb9a6ba17,0xb4b7b2ea,0xbba5bbd0,0xba81ba1b,0xb8a8b92b,0x2d653179,0xbbf9bbe2,0xb89eb807,0xba89bae9,
0xadc99a48,0xbbf8bc00,0xb9afb92b,0xb9a1ba1b,0xb432b1aa,0xbbb8bbe0,0xba93ba27,0xb88eb91d,0xb6d2b587,0xbb3dbb82,0xbb45baf3,0xb6afb7ee,
0xa51b2cb5,0xbc00bbfa,0xb990b900,0xb9c0ba3f,0xb294af40,0xbbd4bbf3,0xba89ba13,0xb89eb935,0xb625b4bd,0xbb63bba4,0xbb47baf0,0xb6a4b7f9,
0xb865b780,0xbab0bb11,0xbbc5bb8f,0xb3a2b540,0xafefa648,0xbbf0bbff,0xba60b9dc,0xb8d6b972,0xb517b31b,0xbb96bbcd,0xbb35bad3,0xb6f4b82d,
0xb7feb693,0xbaeebb4b,0xbbc0bb84,0xb3ebb57c,0xb94ab8ab,0xba00ba7f,0xbbfdbbe9,0xaa7ab0cb,0xb340afd6,0xbbcbbbf1,0xbb0aba99,0xb79bb887,
0xb6d2b540,0xbb3dbb8f,0xbbaebb67,0xb47bb614,0xb8dbb828,0xba5cbad6,0xbbfbbbe0,0xac9cb1aa,0xba15b980,0xb933b9d0,0xbbecbbff,0x30742852,
0xb53ab303,0xbb90bbce,0xbb89bb30,0xb55eb705,0xb83ab6e3,0xbacbbb39,0xbbf2bbca,0xaf8bb34c,0xb9a1b8f6,0xb9afba47,0xbbf5bc00,0x2ec39e48,
0xbac1ba3b,0xb84ab905,0xbb92bbd0,0x352f32ea,0xb6c6b505,0xbb3fbb99,0xbbdcbba0,0xb201b4d5,0xb8fdb838,0xba41bacc,0xbbfebbfb,0x2a16ac83,
0xba50b9b1,0xb8eab99f,0xbbaebbe4,0x347b3147,0xbb4abad9,0xb699b822,0xbaf1bb5d,0x37f33642,0xb820b67c,0xbadbbb50,0xbbffbbe6,0xa884b115,
0xb9afb8f1,0xb9a1ba4b,0xbbd2bbf8,0x32c62db0,0xbae5ba56,0xb80fb8e2,0xbb2abb8c,0x3721354c,0xbbaebb58,0xb47bb659,0xba11baaa,0x3937386d,
0xb8d1b7e3,0xba64baf6,0xbbf2bc00,0x2f8ba248,0xba4db99b,0xb8eeb9b5,0xbb6fbbc1,0x35eb33df,0xbb5cbae3,0xb648b812,0xba6bbafc,0x38c737cd,
0xbbebbbb4,0xb08db451,0xb8f8b9be,0x3a453992,0xb974b89b,0xb9daba8a,0xbbb5bbed,0x344b304e,0xbad5ba33,0xb82ab90e,0xbad8bb58,0x38253659,
0xbbb3bb55,0xb457b665,0xb979ba37,0x39d63909,0xbc00bbed,0x9648b067,0xb764b8a0,0x3b183a87,0xba09b93a,0xb941ba0f,0xbb4abbaf,0x36993475,
0xbb45bab8,0xb6afb858,0xba11babf,0x3937384d,0xbbeabbab,0xb0a6b48d,0xb85ab943,0x3ab63a07,0xbbecbc00,0x30749a48,0xb493b6b5,0x3bab3b43,
0xba8cb9cb,0xb899b984,0xbab3bb46,0x385f36aa,0xbb9cbb28,0xb4f3b726,0xb91fb9fa,0x3a253951,0xbc00bbe4,0xa452b147,0xb631b828,0x3b603ad6,
0xbbb0bbee,0x346f3036,0xae5fb3df,0x3bf63bc1,0xbafeba4f,0xb7c8b8ec,0xb9f4bab5,0x3958385d,0xbbd8bb82,0xb24bb587,0xb80ab90e,0x3ae83a33,
0xbbf3bbfe,0x2f27a97f,0xb2f7b5da,0x3bcf3b72,0xbb4cbbb7,0x368d3438,0x2dc9ac1f,0x3bf83bfc,0xbb5cbac2,0xb648b848,0xb911b9fe,0x3a31394d,
0xbbf9bbc4,0xad33b3ae,0xb5b1b802,0x3b7a3aed,0xbbc5bbf9,0x33a22d1a,0xa94db26f,0x3bfe3bd6,0xbac4bb5d,0x38453642,0x346f2fa4,0x3bb03bf1,
0xbba5bb25,0xb4b7b732,0xb80fb927,0x3ae53a1f,0xbbffbbee,0x2884b036,0xb24bb5b6,0x3bd83b79,0xbb76bbd6,0x35c8326f,0x305ba7da,0x3bed3bff,
0xba19bae0,0x392e3817,0x374234c9,0x3b213ba2,0xbbd9bb77,0xb232b5c2,0xb5ebb832,0x3b6f3ad0,0xbbe8bc00,0x30d7a57f,0xa81fb288,0x3bff3bd5,
0xbb07bb95,0x37a6351d,0x34f33080,0x3b9c3bec,0xb94fba43,0x39fc38fb,0x38ea3780,0x3a503b11,0xbbf8bbb6,0xadc9b444,0xb328b64e,0x3bcc3b5a,
0xbbb7bbf8,0x343e2db0,0x3042a9e3,0x3bee3bfe,0xba7abb36,0x38b236ee,0x379034ed,0x3b0d3b9d,0xb86ab989,0x3aac39c7,0x3a0438fb,0x39463a43,
0xbc00bbe2,0x2311b179,0xac9cb414,0x3bfb3bbc,0xbb6abbd7,0x36023257,0x34b72f40,0x3ba53bf3,0xb9d2babc,0x397d3852,0x38f83775,0x3a453b14,
0xb6ddb8b5,0x3b3a3a78,0x3ae83a0b,0x380a393e,0xbbf2bbfa,0x2f8bacb5,0x2d33af0e,0x3bf93bf4,0xbb04bb9e,0x37b234e1,0x372c3451,0x3b273bb4,
0xb911ba27,0x3a31391d,0x3a0038e2,0x394a3a56,0xb4c3b796,0x3ba33b0b,0x3b8b3ae6,0x3552380d,0x4c004c00,0x26480000,0x4c004c00,0x33113248,
0x4c004c00,0x2cb62a48,0x4c004c00,0x345233db,0x4c004c00,0x2fdb2e48,0x4c004c00,0x351b34b6,0x4c004c00,0x317f30b6,0x4bff4c00,0x35e4357f,
0x4c004c00,0x2fdb0000,0x4bfb4bfc,0x3c6a3bd9,0x4bff4c00,0x35e433db,0x4bf94bfa,0x3d653ce7,0x4bfe4bff,0x38e837da,0x4bf64bf7,0x3e5f3de2,
0x4bfd4bfe,0x3ade39e3,0x4bf24bf4,0x3f593edc,0x4c004c00,0x33110000,0x4bf04bf4,0x3fef3f0e,0x4bfe4bff,0x394d3711,0x4be84bed,0x40d74067,
0x4bfb4bfd,0x3c6a3b11,0x4bdf4be4,0x41b64147,0x4bf64bf9,0x3e2d3d4c,0x4bd44bda,0x42944226,0x4c004c00,0x351b0000,0x4bdf4be6,0x41b64115,
0x4bfc4bfe,0x3ba7391b,0x4bcf4bd7,0x42f74257,0x4bf64bf9,0x3e5f3d1a,0x4bbc4bc6,0x441a4396,0x4bec4bf1,0x40743fa4,0x4ba54bb1,0x44b74469,
0x4bff4c00,0x36ad0000,0x4bc84bd4,0x437142a1,0x4bfa4bfd,0x3d003aac,0x4bac4bbb,0x44874420,0x4bef4bf5,0x40293eaa,0x4b8b4b9d,0x455244ed,
0x4bde4be7,0x41cf40fd,0x4b654b79,0x461a45b6,0x4bff4c00,0x381f0000,0x4bab4bbc,0x44934414,0x4bf64bfc,0x3e2d3c1f,0x4b814b97,0x458d4511,
0x4be54bef,0x4122401d,0x4b4f4b69,0x46824608,0x4bcc4bda,0x43284226,0x4b164b33,0x476f46f9,0x4bfe4c00,0x38e80000,0x4b874ba0,0x456a44d5,
0x4bf24bfa,0x3f593ce7,0x4b4c4b6b,0x468d45fd,0x4bda4be8,0x421940e4,0x4b074b2b,0x47a6471b,0x4bb74bca,0x443e434c,0x4ab64ae0,0x485a4817,
0x4bfe4c00,0x39b10000,0x4b5e4b80,0x463c4593,0x4bee4bf8,0x40423db0,0x4b104b39,0x478546e3,0x4bce4be0,0x430f41aa,0x4ab34ae3,0x485f4812,
0x4b9e4bb7,0x44e74438,0x4a494a7f,0x48f348ab,0x4bfd4c00,0x3a7a0000,0x4b2f4b5a,0x470a464e,0x4be84bf6,0x40d73e78,0x4acb4aff,0x483a47c2,
0x4bbf4bd6,0x4402426f,0x4a544a92,0x48e54891,0x4b814ba2,0x458d44c9,0x49cd4a13,0x49824935,0x4bfd4c00,0x3b430000,0x4afb4b30,0x47d24705,
0x4be24bf3,0x416c3f40,0x4a7e4abf,0x48ad484d,0x4bae4bcb,0x447b4334,0x49eb4a37,0x49624909,0x4b604b8a,0x46314558,0x4946499b,0x4a0449b5,
0x4bfc4c00,0x3c060000,0x4ac14b02,0x484a47b7,0x4bdc4bf0,0x42014004,0x4a294a78,0x491b48b5,0x4b9c4bc0,0x44f343f7,0x497949d4,0x49d6497b,
0x4b3d4b70,0x46d245e5,0x48b24918,0x4a7a4a2b,0x4bfb4c00,0x3c6a0000,0x4a814ad0,0x48a84832,0x4bd44bed,0x42944067,0x49cd4a2b,0x49824918,
0x4b874bb2,0x456a445d,0x48fd4969,0x4a4149e5,0x4b164b53,0x476f4670,0x4815488c,0x4ae14a95,0x4bfa4c00,0x3cce0000,0x4a3d4a99,0x49024887,
0x4bcc4be9,0x432840cb,0x496b49d8,0x49e34976,0x4b714ba4,0x45df44bd,0x487a48f6,0x4aa24a47,0x4aeb4b33,0x480546f9,0x46dd47ee,0x4b3a4af3,
0x4bf94c00,0x3d330000,0x49f44a5e,0x495848d8,0x4bc34be5,0x43ba412e,0x49024980,0x4a3d49d0,0x4b594b95,0x4654451d,0x47dd487c,0x4af74aa0,
0x4abd4b11,0x48504780,0x458146b5,0x4b834b43,0x4bf84c00,0x3d970000,0x49a64a1f,0x49aa4927,0x4bba4be1,0x44264191,0x48944922,0x4a904a23,
0x4b3f4b84,0x46c6457c,0x46bb47f9,0x4b424af0,0x4a8c4aed,0x48994802,0x441a4570,0x4bbc4b86,0x4bf74c00,0x3dfb0000,0x495449dc,0x49f84972,
0x4bb04bdc,0x446f41f4,0x482048bf,0x4adb4a71,0x4b244b72,0x473745da,0x458d46ee,0x4b814b36,0x4a584ac6,0x48e04842,0x41534420,0x4be34bbb,
0x4bf64c00,0x3e5f0000,0x48fd4996,0x4a4149ba,0x4ba54bd7,0x44b74257,0x474e4858,0x4b1e4ab8,0x4b074b5f,0x47a64637,0x445745da,0x4bb34b72,
0x4a214a9c,0x49244881,0x3cce4191,0x4bfa4be1,0x4bf54c00,0x3ec30000,0x48a3494d,0x4a8549fe,0x4b9a4bd2,0x44ff42b9,0x465447d8,0x4b594af9,
0x4ae84b4b,0x480a4693,0x423244bd,0x4bd94ba4,0x49e74a71,0x496648bf,0xb4523db0,0x4c004bf8,0x4bf34c00,0x3f270000,0x48454900,0x4ac44a3f,
0x4b8e4bcd,0x4546431b,0x455246f9,0x4b8b4b33,0x4ac74b36,0x484046ee,0x3f594334,0x4bf24bcb,0x49aa4a43,0x49a648fb,0xbef52a48,0x4bf44c00,
0x4bf24c00,0x3f8b0000,0x47c848b0,0x4afe4a7c,0x4b814bc7,0x458d437d,0x444b4614,0x4bb54b67,0x4aa54b20,0x48744748,0x388440e4,0x4bff4be8,
0x496b4a13,0x49e34935,0xc263bd4c,0x4bd74bf9,0x4bf04c00,0x3fef0000,0x46ff485d,0x4b324ab5,0x4b734bc1,0x45d443df,0x427c4529,0x4bd64b93,
0x4a814b08,0x48a847a1,0xb9b13d1a,0x4bfe4bf9,0x492949e1,0x4a1d496d,0xc49fc160,0x4ba94be3,0x4bef4c00,0x40290000,0x46314807,0x4b604ae9,
0x4b654bbb,0x461a4420,0x405b4438,0x4bed4bb7,0x4a5c4af0,0x48db47f9,0xbfef2e48,0x4bf04c00,0x48e549ad,0x4a5449a4,0xc602c408,0x4b6a4bbe,
0x4bed4c00,0x405b0000,0x455e475e,0x4b894b1a,0x4b574bb4,0x465f4451,0x3c6a4288,0x4bfb4bd5,0x4a354ad6,0x490c4828,0xc27cbc51,0x4bd64bfb,
0x489e4976,0x4a8949d8,0xc759c558,0x4b1b4b8a,0x4beb4c00,0x408d0000,0x448746aa,0x4bac4b46,0x4b474bad,0x46a44481,0x26484099,0x4c004beb,
0x4a0d4abc,0x493c4852,0xc47bc080,0x4bae4bec,0x4855493e,0x4aba4a0b,0xc850c69e,0x4abd4b49,0x4be94c00,0x40be0000,0x435945f1,0x4bc94b6e,
0x4b374ba6,0x46e844b1,0xbc383d4c,0x4bfc4bf9,0x49e34aa0,0x496b487c,0xc5b1c2d2,0x4b7a4bd1,0x480a4905,0x4ae84a3b,0xc8eac7d8,0x4a504af9,
0x4be74c00,0x40f00000,0x419e4534,0x4be04b91,0x4b274b9e,0x472c44e1,0xc042357f,0x4bee4c00,0x49b84a83,0x499948a6,0xc6ddc48d,0x4b3a4bab,
0x477a48c9,0x4b134a69,0xc979c881,0x49d64a9c,0x4be54c00,0x41220000,0x3fbd4475,0x4bf14baf,0x4b164b97,0x476f4511,0xc263b91b,0x4bd74bfe,
0x498b4a65,0x49c548ce,0xc7fec5ab,0x4aee4b7b,0x46dd488c,0x4b3a4a95,0xc9fcc90e,0x494f4a33,0x4be34c00,0x41530000,0x3c384365,0x4bfc4bc9,
0x4b044b8f,0x47b24540,0xc43ebe78,0x4bb74bf6,0x495d4a47,0x49f048f6,0xc889c6c1,0x4a974b41,0x463c484d,0x4b5e4abf,0xca73c992,0x48bc49be,
0x4be14c00,0x41850000,0x317f41db,0x4c004bdd,0x4af14b86,0x47f34570,0xc546c12e,0x4b8e4be5,0x492e4a27,0x4a19491d,0xc90cc7cd,0x4a354afc,
0x4599480d,0x4b7f4ae6,0xcadbca0b,0x4820493e,0x4bdf4c00,0x41b60000,0xb9b1404e,0x4bfe4bed,0x4ade4b7d,0x481a459f,0xc648c31b,0x4b5c4bcd,
0x48fd4a07,0x4a414943,0xc986c867,0x49c94aae,0x44f34796,0x4b9c4b0b,0xcb35ca78,0x46f448b5,0x4bdd4c00,0x41e80000,0xbe5f3d7e,0x4bf64bf8,
0x4acb4b74,0x483a45ce,0xc742c481,0x4b214bad,0x48cc49e5,0x4a674969,0xc9f8c8e2,0x49544a56,0x444b4710,0x4bb54b2e,0xcb7fcad9,0x45994822,
0x4bda4c00,0x42190000,0xc0f038b6,0x4be74bff,0x4ab64b6b,0x485a45fd,0xc81ac570,0x4ade4b86,0x489949c3,0x4a8c498d,0xca60c956,0x48d649f6,
0x43404687,0x4bcb4b4e,0xcbb8cb2e,0x44324710,0x4bd84c00,0x424b0000,0xc2adb248,0x4bd34c00,0x4aa24b62,0x487a462b,0xc88ec659,0x4a934b58,
0x4865499f,0x4ab049b1,0xcabdc9c3,0x4850498d,0x41e845fd,0x4bdd4b6b,0xcbe1cb74,0x418545ce,0x4bd64c00,0x427c0000,0xc432bbd9,0x4bb84bfc,
0x4a8c4b58,0x48994659,0xc8fdc73d,0x4a414b22,0x4830497b,0x4ad149d4,0xcb10ca27,0x4785491d,0x408d4570,0x4beb4b86,0xcbf9cbad,0x3d334481,
0x4bd34c00,0x42ad0000,0xc50bbf0e,0x4b984bf4,0x4a764b4e,0x48b74687,0xc966c80d,0x49e74ae6,0x47f34956,0x4af149f6,0xcb57ca83,0x465f48a6,
0x3e5f44e1,0x4bf64b9e,0xcc00cbd7,0xb17f4257,0x4bd04c00,0x42de0000,0xc5dfc115,0x4b714be6,0x4a604b43,0x48d646b5,0xc9c9c877,0x49864aa3,
0x47854930,0x4b104a17,0xcb92cad6,0x452f4828,0x3b434451,0x4bfd4bb4,0xcbf5cbf3,0xbe913f40,0x4bce4c00,0x430f0000,0xc6afc2a1,0x4b454bd4,
0x4a494b39,0x48f346e3,0xca25c8dd,0x491f4a5a,0x47154909,0x4b2c4a37,0xcbc0cb20,0x43eb4748,0x3311437d,0x4c004bc7,0xcbd9cbff,0xc2323711,
0x4bcb4c00,0x43400000,0xc77ac414,0x4b134bbc,0x4a314b2e,0x49114710,0xca7ac93e,0x48b24a0b,0x46a448e2,0x4b474a56,0xcbe2cb5f,0x416c4637,
0xb7764257,0x4bff4bd7,0xcbaccbfd,0xc487bb75,0x4bc84c00,0x43710000,0xc820c4d5,0x4adb4ba0,0x4a194b22,0x492e473d,0xcac7c99b,0x484049b5,
0x463148ba,0x4b604a74,0xcbf8cb95,0x3dc9451d,0xbc9c412e,0x4bfb4be5,0xcb6fcbeb,0xc5ebc099,0x4bc54c00,0x43a20000,0xc87fc593,0x4a9e4b80,
0x4a004b17,0x494a476a,0xcb0dc9f2,0x4790495b,0x45bc4891,0x4b784a92,0xcc00cbc0,0x317f43f7,0xbf594004,0x4bf24bf0,0xcb21cbca,0xc742c34c,
0x4bc24c00,0x43d30000,0xc8dbc64e,0x4a5c4b5a,0x49e74b0b,0x49664796,0xcb4aca43,0x469948fb,0x45464867,0x4b8e4aae,0xcbfbcbe0,0xbc6a41aa,
0xc1093db0,0x4be64bf8,0xcac4cb9b,0xc845c4f9,0x4bbf4c00,0x44020000,0xc933c705,0x4a154b30,0x49cd4aff,0x498247c2,0xcb7fca8e,0x45994896,
0x44cf483d,0x4ba14ac9,0xcbe9cbf5,0xc0be3eaa,0xc2633aac,0x4bd74bfd,0xca58cb5d,0xc8e0c642,0x4bbc4c00,0x441a0000,0xc986c7b7,0x49c94b02,
0x49b34af3,0x499d47ee,0xcbabcad3,0x4493482d,0x44574812,0x4bb34ae3,0xcbcbcbff,0xc34037da,0xc3ba33db,0x4bc34c00,0xc9dfcb11,0xc970c780,
0x4bb84c00,0x44320000,0xc9d6c832,0x49794ad0,0x49994ae6,0x49b8480d,0xcbcecb11,0x430f4780,0x43ba47cd,0x4bc34afc,0xcb9fcbfe,0xc4dbb97f,
0xc487b57f,0x4bac4c00,0xc958cab8,0xc9f4c858,0x4bb54c00,0x444b0000,0xca21c887,0x49244a99,0x497d4ad9,0x49d24822,0xcbe7cb49,0x40f0469e,
0x42c64775,0x4bd24b14,0xcb68cbf2,0xc60ebf72,0xc52fbb75,0x4b924bfd,0xc8c7ca52,0xca6bc8e7,0x4bb24c00,0x44630000,0xca67c8d8,0x48cc4a5e,
0x49624acc,0x49eb4838,0xcbf8cb79,0x3d9745b6,0x41cf471b,0x4bde4b2b,0xcb24cbdb,0xc737c20d,0xc5d4be14,0x4b734bf7,0xc82ac9e1,0xcad5c96d,
0x4bae4c00,0x447b0000,0xcaa9c927,0x486f4a1f,0x49464abf,0x4a04484d,0xcc00cba2,0x351b44c9,0x40d746c1,0x4be84b41,0xcad5cbb9,0xc82ac42c,
0xc676c036,0x4b524bee,0xc70ac964,0xcb2fc9e9,0x4bab4c00,0x44930000,0xcae5c972,0x480f49dc,0x49294ab1,0x4a1d4862,0xcbfecbc4,0xba1643ae,
0x3fbd4665,0x4bf14b55,0xca7acb8c,0xc8b2c54c,0xc715c160,0x4b2c4be3,0xc5b1c8dd,0xcb7aca5a,0x4ba74c00,0x44ab0000,0xcb1bc9ba,0x47594996,
0x490c4aa3,0x4a354877,0xcbf2cbdf,0xbf5941c3,0x3dc94608,0x4bf84b69,0xca15cb55,0xc933c665,0xc7b2c288,0x4b044bd5,0xc44bc84d,0xcbb5cabf,
0x4ba34c00,0x44c30000,0xcb4cc9fe,0x468d494d,0x48ee4a95,0x4a4d488c,0xcbdecbf1,0xc1cf3fa4,0x3ba745ab,0x4bfc4b7b,0xc9a6cb14,0xc9aac775,
0xc825c3ae,0x4ad84bc4,0xc1b6c76a,0xcbdfcb17,0x4b9f4c00,0x44db0000,0xcb78ca3f,0x45bc4900,0x48d14a87,0x4a6448a0,0xcbc0cbfd,0xc3eb3b75,
0x3776454c,0x4bff4b8c,0xc92ecac9,0xca19c83d,0xc86fc469,0x4aa94bb1,0xbd97c62b,0xcbf8cb62,0x4b9c4c00,0x44f30000,0xcb9eca7c,0x44e748b0,
0x48b24a78,0x4a7a48b5,0xcb9acc00,0xc4ffaa48,0xa64844ed,0x4c004b9d,0xc8adca74,0xca7ec8ba,0xc8b7c4f9,0x4a764b9b,0x2cb6c4e1,0xcc00cb9e,
0x4b984c00,0x450b0000,0xcbbdcab5,0x440e485d,0x48944a69,0x4a9048c9,0xcb6acbfc,0xc602bc1f,0xb81f448d,0x4bff4bab,0xc825ca17,0xcad8c930,
0xc8fdc587,0x4a414b82,0x3e2dc31b,0xcbf6cbcd,0x4b944c00,0x45230000,0xcbd7cae9,0x42634807,0x48744a5a,0x4aa548dd,0xcb32cbf0,0xc6ffc004,
0xbc06442c,0x4bfc4bb9,0xc72cc9b1,0xcb27c99f,0xc941c614,0x4a094b67,0x4201c067,0xcbdccbed,0x4b904c00,0x453a0000,0xcbeacb1a,0x40a6475e,
0x48554a4b,0x4aba48f1,0xcaf1cbdc,0xc7f3c1f4,0xbdfb4396,0x4bf74bc6,0xc602c943,0xcb6aca07,0xc982c69e,0x49cd4b49,0x446fbaac,0xcbb0cbfd,
0x4b8b4c00,0x45520000,0xcbf8cb46,0x3dc946aa,0x48354a3b,0x4ace4905,0xcaa9cbc1,0xc86fc3df,0xbfef42d2,0x4bf04bd1,0xc4cfc8ce,0xcba1ca65,
0xc9c0c726,0x49904b28,0x45d43852,0xcb73cbff,0x4b874c00,0x456a0000,0xcbffcb6e,0x388445f1,0x48154a2b,0x4ae14918,0xca58cb9e,0xc8e0c4e1,
0xc0f0420d,0x4be74bdb,0xc328c852,0xcbcccabc,0xc9fcc7ac,0x494f4b05,0x472c3fa4,0xcb27cbf1,0x4b834c00,0x45810000,0xcc00cb91,0xb51b4534,
0x47e84a1b,0x4af4492b,0xca00cb74,0xc94ac5ce,0xc1e84147,0x4bdd4be4,0xc0a6c7a1,0xcbeacb08,0xca35c817,0x490c4ae0,0x483a4288,0xcacbcbd5,
0x4b7f4c00,0x45990000,0xcbfacbaf,0xbcce4475,0x47a64a0b,0x4b07493e,0xc9a1cb43,0xc9afc6b5,0xc2de4080,0x4bd04bec,0xbc38c693,0xcbfccb4b,
0xca6bc858,0x48c74ab8,0x48d64499,0xca60cbaa,0x4b7a4c00,0x45b10000,0xcbefcbc9,0xc0294365,0x476449fa,0x4b184951,0xc93ccb0b,0xca0dc796,
0xc3d33f72,0x4bc24bf2,0x3311c57c,0xcc00cb84,0xca9ec896,0x487f4a8e,0x496645e5,0xc9e7cb70,0x4b764c00,0x45c80000,0xcbddcbdd,0xc1e841db,
0x472149e9,0x4b2a4964,0xc8d1cacc,0xca64c838,0xc4633de2,0x4bb24bf7,0x3dfbc45d,0xcbf7cbb2,0xcacec8d3,0x48354a62,0x49eb4726,0xc962cb28,
0x4b714c00,0x45df0000,0xcbc5cbed,0xc3a2404e,0x46dd49d8,0x4b3a4976,0xc85fca87,0xcab3c8a0,0xc4db3c51,0x4b9f4bfb,0x4185c26f,0xcbe1cbd6,
0xcafbc90e,0x47d24a33,0x4a64482d,0xc8d1cad3,0x4b6c4c00,0x45f70000,0xcba7cbf8,0xc4ab3d7e,0x469949c7,0x4b4a4989,0xc7d2ca3b,0xcafbc905,
0xc552397f,0x4b8b4bfe,0x4402c01d,0xcbbfcbef,0xcb24c948,0x47374a02,0x4ace48bf,0xc835ca71,0x4b684c00,0x460e0000,0xcb83cbff,0xc58138b6,
0x465449b5,0x4b59499b,0xc6ddc9e9,0xcb3ac964,0xc5c834b6,0x4b764c00,0x453abb11,0xcb90cbfd,0xcb4ac980,0x469949d0,0x4b2a4948,0xc721ca02,
0x2c002c00,0x2c002c00,0x2c002c00,0x2c002c00,0x2b642c00,0x261f29a8,0xa61f0000,0xab64a9a8,0x29a82c00,0xa9a80000,0xa9a8ac00,0x29a80000,
0x261f2c00,0xab64a9a8,0x2b640000,0xa61f29a8,0x2c00,0xac00,0x2c00,0xac00,0xa61f2c00,0x2b64a9a8,0xab640000,0x261f29a8,
0xa9a82c00,0x29a80000,0x29a8ac00,0xa9a80000,0xab642c00,0xa61f29a8,0x261f0000,0x2b64a9a8,0,0,0,0,
0x261f0000,0x2b6429a8,0x2b642c00,0x261f29a8,0x29a80000,0x29a82c00,0xa9a80000,0xa9a8ac00,0x2b640000,0xa61f29a8,0xa61fac00,0x2b6429a8,
0x2c000000,0xac000000,0x2c000000,0xac000000,0x2b640000,0xa61fa9a8,0xa61f2c00,0x2b64a9a8,0x29a80000,0x29a8ac00,0xa9a80000,0xa9a82c00,
0x261f0000,0x2b64a9a8,0x2b64ac00,0x261fa9a8,0xac002c00,0xac002c00,0xac002c00,0xac002c00,0xab642c00,0xa61f29a8,0x261f0000,0x2b64a9a8,
0xa9a82c00,0x29a80000,0x29a8ac00,0xa9a80000,0xa61f2c00,0x2b64a9a8,0xab640000,0x261f29a8,0x2c00,0xac00,0x2c00,0xac00,
0x261f2c00,0xab64a9a8,0x2b640000,0xa61f29a8,0x29a82c00,0xa9a80000,0xa9a8ac00,0x29a80000,0x2b642c00,0x261f29a8,0xa61f0000,0xab64a9a8,
0,0,0,0,0xa61f0000,0xab6429a8,0xab642c00,0xa61f29a8,0xa9a80000,0xa9a82c00,0x29a80000,0x29a8ac00,
0xab640000,0x261f29a8,0x261fac00,0xab6429a8,0xac000000,0x2c000000,0xac000000,0x2c000000,0xab640000,0x261fa9a8,0x261f2c00,0xab64a9a8,
0xa9a80000,0xa9a8ac00,0x29a80000,0x29a82c00,0xa61f0000,0xab64a9a8,0xab64ac00,0xa61fa9a8,0,0,0,0,
0xa61f0000,0xab64a9a8,0xab64ac00,0xa61fa9a8,0xa9a80000,0xa9a8ac00,0x29a80000,0x29a82c00,0xab640000,0x261fa9a8,0x261f2c00,0xab64a9a8,
0xac000000,0x2c000000,0xac000000,0x2c000000,0xab640000,0x261f29a8,0x261fac00,0xab6429a8,0xa9a80000,0xa9a82c00,0x29a80000,0x29a8ac00,
0xa61f0000,0xab6429a8,0xab642c00,0xa61f29a8,0x2c002c00,0x2c002c00,0x2c002c00,0x2c002c00,0x2b642c00,0x261f29a8,0xa61f0000,0xab64a9a8,
0x29a82c00,0xa9a80000,0xa9a8ac00,0x29a80000,0x261f2c00,0xab64a9a8,0x2b640000,0xa61f29a8,0x2c00,0xac00,0x2c00,0xac00,
0xa61f2c00,0x2b64a9a8,0xab640000,0x261f29a8,0xa9a82c00,0x29a80000,0x29a8ac00,0xa9a80000,0xab642c00,0xa61f29a8,0x261f0000,0x2b64a9a8,
0,0,0,0,0x261f0000,0x2b64a9a8,0x2b64ac00,0x261fa9a8,0x29a80000,0x29a8ac00,0xa9a80000,0xa9a82c00,
0x2b640000,0xa61fa9a8,0xa61f2c00,0x2b64a9a8,0x2c000000,0xac000000,0x2c000000,0xac000000,0x2b640000,0xa61f29a8,0xa61fac00,0x2b6429a8,
0x29a80000,0x29a82c00,0xa9a80000,0xa9a8ac00,0x261f0000,0x2b6429a8,0x2b642c00,0x261f29a8,0xac002c00,0xac002c00,0xac002c00,0xac002c00,
0xab642c00,0xa61f29a8,0x261f0000,0x2b64a9a8,0xa9a82c00,0x29a80000,0x29a8ac00,0xa9a80000,0xa61f2c00,0x2b64a9a8,0xab640000,0x261f29a8,
0x2c00,0xac00,0x2c00,0xac00,0x261f2c00,0xab64a9a8,0x2b640000,0xa61f29a8,0x29a82c00,0xa9a80000,0xa9a8ac00,0x29a80000,
0x2b642c00,0x261f29a8,0xa61f0000,0xab64a9a8,0x2c002c00,0x2c002c00,0x2c002c00,0x2c002c00,0xab64ac00,0xa61fa9a8,0x261f0000,0x2b6429a8,
0x29a82c00,0xa9a80000,0xa9a8ac00,0x29a80000,0xa61fac00,0x2b6429a8,0xab640000,0x261fa9a8,0x2c00,0xac00,0x2c00,0xac00,
0x261fac00,0xab6429a8,0x2b640000,0xa61fa9a8,0xa9a82c00,0x29a80000,0x29a8ac00,0xa9a80000,0x2b64ac00,0x261fa9a8,0xa61f0000,0xab6429a8,
0,0,0,0,0xa61f0000,0xab64a9a8,0xab64ac00,0xa61fa9a8,0x29a80000,0x29a82c00,0xa9a80000,0xa9a8ac00,
0xab640000,0x261fa9a8,0x261f2c00,0xab64a9a8,0x2c000000,0xac000000,0x2c000000,0xac000000,0xab640000,0x261f29a8,0x261fac00,0xab6429a8,
0x29a80000,0x29a8ac00,0xa9a80000,0xa9a82c00,0xa61f0000,0xab6429a8,0xab642c00,0xa61f29a8,0xac002c00,0xac002c00,0xac002c00,0xac002c00,
0x2b64ac00,0x261fa9a8,0xa61f0000,0xab6429a8,0xa9a82c00,0x29a80000,0x29a8ac00,0xa9a80000,0x261fac00,0xab6429a8,0x2b640000,0xa61fa9a8,
0x2c00,0xac00,0x2c00,0xac00,0xa61fac00,0x2b6429a8,0xab640000,0x261fa9a8,0x29a82c00,0xa9a80000,0xa9a8ac00,0x29a80000,
0xab64ac00,0xa61fa9a8,0x261f0000,0x2b6429a8,0,0,0,0,0x261f0000,0x2b64a9a8,0x2b64ac00,0x261fa9a8,
0xa9a80000,0xa9a82c00,0x29a80000,0x29a8ac00,0x2b640000,0xa61fa9a8,0xa61f2c00,0x2b64a9a8,0xac000000,0x2c000000,0xac000000,0x2c000000,
0x2b640000,0xa61f29a8,0xa61fac00,0x2b6429a8,0xa9a80000,0xa9a8ac00,0x29a80000,0x29a82c00,0x261f0000,0x2b6429a8,0x2b642c00,0x261f29a8,
0,0,0,0,0x261f0000,0x2b6429a8,0x2b642c00,0x261f29a8,0xa9a80000,0xa9a8ac00,0x29a80000,0x29a82c00,
0x2b640000,0xa61f29a8,0xa61fac00,0x2b6429a8,0xac000000,0x2c000000,0xac000000,0x2c000000,0x2b640000,0xa61fa9a8,0xa61f2c00,0x2b64a9a8,
0xa9a80000,0xa9a82c00,0x29a80000,0x29a8ac00,0x261f0000,0x2b64a9a8,0x2b64ac00,0x261fa9a8,0x2c002c00,0x2c002c00,0x2c002c00,0x2c002c00,
0xab64ac00,0xa61fa9a8,0x261f0000,0x2b6429a8,0x29a82c00,0xa9a80000,0xa9a8ac00,0x29a80000,0xa61fac00,0x2b6429a8,0xab640000,0x261fa9a8,
0x2c00,0xac00,0x2c00,0xac00,0x261fac00,0xab6429a8,0x2b640000,0xa61fa9a8,0xa9a82c00,0x29a80000,0x29a8ac00,0xa9a80000,
0x2b64ac00,0x261fa9a8,0xa61f0000,0xab6429a8,0,0,0,0,0xa61f0000,0xab6429a8,0xab642c00,0xa61f29a8,
0x29a80000,0x29a8ac00,0xa9a80000,0xa9a82c00,0xab640000,0x261f29a8,0x261fac00,0xab6429a8,0x2c000000,0xac000000,0x2c000000,0xac000000,
0xab640000,0x261fa9a8,0x261f2c00,0xab64a9a8,0x29a80000,0x29a82c00,0xa9a80000,0xa9a8ac00,0xa61f0000,0xab64a9a8,0xab64ac00,0xa61fa9a8,
0xac002c00,0xac002c00,0xac002c00,0xac002c00,0x2b64ac00,0x261fa9a8,0xa61f0000,0xab6429a8,0xa9a82c00,0x29a80000,0x29a8ac00,0xa9a80000,
0x261fac00,0xab6429a8,0x2b640000,0xa61fa9a8,0x2c00,0xac00,0x2c00,0xac00,0xa61fac00,0x2b6429a8,0xab640000,0x261fa9a8,
0x29a82c00,0xa9a80000,0xa9a8ac00,0x29a80000,0xab64ac00,0xa61fa9a8,0x261f0000,0x2b6429a8,0x2bd92c00,0x2aa72b64,0x287229a8,0x223e261f,
0x2aa72c00,0xa23e261f,0xabd9a9a8,0xa872ab64,0x28722c00,0xabd9a61f,0x223ea9a8,0x2aa72b64,0x223e2c00,0xa872ab64,0x2aa729a8,0xabd9a61f,
0xa23e2c00,0x2872ab64,0xaaa729a8,0x2bd9a61f,0xa8722c00,0x2bd9a61f,0xa23ea9a8,0xaaa72b64,0xaaa72c00,0x223e261f,0x2bd9a9a8,0x2872ab64,
0xabd92c00,0xaaa72b64,0xa87229a8,0xa23e261f,0x223e0000,0x2872261f,0x2aa729a8,0x2bd92b64,0x28720000,0x2bd92b64,0x223e29a8,0xaaa7a61f,
0x2aa70000,0x223e2b64,0xabd9a9a8,0x2872a61f,0x2bd90000,0xaaa7261f,0x2872a9a8,0xa23e2b64,0x2bd90000,0xaaa7a61f,0x287229a8,0xa23eab64,
0x2aa70000,0x223eab64,0xabd929a8,0x2872261f,0x28720000,0x2bd9ab64,0x223ea9a8,0xaaa7261f,0x223e0000,0x2872a61f,0x2aa7a9a8,0x2bd9ab64,
0xabd92c00,0xaaa72b64,0xa87229a8,0xa23e261f,0xaaa72c00,0x223e261f,0x2bd9a9a8,0x2872ab64,0xa8722c00,0x2bd9a61f,0xa23ea9a8,0xaaa72b64,
0xa23e2c00,0x2872ab64,0xaaa729a8,0x2bd9a61f,0x223e2c00,0xa872ab64,0x2aa729a8,0xabd9a61f,0x28722c00,0xabd9a61f,0x223ea9a8,0x2aa72b64,
0x2aa72c00,0xa23e261f,0xabd9a9a8,0xa872ab64,0x2bd92c00,0x2aa72b64,0x287229a8,0x223e261f,0xa23e0000,0xa872261f,0xaaa729a8,0xabd92b64,
0xa8720000,0xabd92b64,0xa23e29a8,0x2aa7a61f,0xaaa70000,0xa23e2b64,0x2bd9a9a8,0xa872a61f,0xabd90000,0x2aa7261f,0xa872a9a8,0x223e2b64,
0xabd90000,0x2aa7a61f,0xa87229a8,0x223eab64,0xaaa70000,0xa23eab64,0x2bd929a8,0xa872261f,0xa8720000,0xabd9ab64,0xa23ea9a8,0x2aa7261f,
0xa23e0000,0xa872a61f,0xaaa7a9a8,0xabd9ab64,0xa23e0000,0xa872a61f,0xaaa7a9a8,0xabd9ab64,0xa8720000,0xabd9ab64,0xa23ea9a8,0x2aa7261f,
0xaaa70000,0xa23eab64,0x2bd929a8,0xa872261f,0xabd90000,0x2aa7a61f,0xa87229a8,0x223eab64,0xabd90000,0x2aa7261f,0xa872a9a8,0x223e2b64,
0xaaa70000,0xa23e2b64,0x2bd9a9a8,0xa872a61f,0xa8720000,0xabd92b64,0xa23e29a8,0x2aa7a61f,0xa23e0000,0xa872261f,0xaaa729a8,0xabd92b64,
0x2bd92c00,0x2aa72b64,0x287229a8,0x223e261f,0x2aa72c00,0xa23e261f,0xabd9a9a8,0xa872ab64,0x28722c00,0xabd9a61f,0x223ea9a8,0x2aa72b64,
0x223e2c00,0xa872ab64,0x2aa729a8,0xabd9a61f,0xa23e2c00,0x2872ab64,0xaaa729a8,0x2bd9a61f,0xa8722c00,0x2bd9a61f,0xa23ea9a8,0xaaa72b64,
0xaaa72c00,0x223e261f,0x2bd9a9a8,0x2872ab64,0xabd92c00,0xaaa72b64,0xa87229a8,0xa23e261f,0x223e0000,0x2872a61f,0x2aa7a9a8,0x2bd9ab64,
0x28720000,0x2bd9ab64,0x223ea9a8,0xaaa7261f,0x2aa70000,0x223eab64,0xabd929a8,0x2872261f,0x2bd90000,0xaaa7a61f,0x287229a8,0xa23eab64,
0x2bd90000,0xaaa7261f,0x2872a9a8,0xa23e2b64,0x2aa70000,0x223e2b64,0xabd9a9a8,0x2872a61f,0x28720000,0x2bd92b64,0x223e29a8,0xaaa7a61f,
0x223e0000,0x2872261f,0x2aa729a8,0x2bd92b64,0xabd92c00,0xaaa72b64,0xa87229a8,0xa23e261f,0xaaa72c00,0x223e261f,0x2bd9a9a8,0x2872ab64,
0xa8722c00,0x2bd9a61f,0xa23ea9a8,0xaaa72b64,0xa23e2c00,0x2872ab64,0xaaa729a8,0x2bd9a61f,0x223e2c00,0xa872ab64,0x2aa729a8,0xabd9a61f,
0x28722c00,0xabd9a61f,0x223ea9a8,0x2aa72b64,0x2aa72c00,0xa23e261f,0xabd9a9a8,0xa872ab64,0x2bd92c00,0x2aa72b64,0x287229a8,0x223e261f,
0xa23e0000,0xa872a61f,0xaaa7a9a8,0xabd9ab64,0x28720000,0x2bd92b64,0x223e29a8,0xaaa7a61f,0xaaa70000,0xa23eab64,0x2bd929a8,0xa872261f,
0x2bd90000,0xaaa7261f,0x2872a9a8,0xa23e2b64,0xabd90000,0x2aa7261f,0xa872a9a8,0x223e2b64,0x2aa70000,0x223eab64,0xabd929a8,0x2872261f,
0xa8720000,0xabd92b64,0xa23e29a8,0x2aa7a61f,0x223e0000,0x2872a61f,0x2aa7a9a8,0x2bd9ab64,0x2bd92c00,0x2aa72b64,0x287229a8,0x223e261f,
0xaaa7ac00,0x223ea61f,0x2bd929a8,0x28722b64,0x28722c00,0xabd9a61f,0x223ea9a8,0x2aa72b64,0xa23eac00,0x28722b64,0xaaa7a9a8,0x2bd9261f,
0xa23e2c00,0x2872ab64,0xaaa729a8,0x2bd9a61f,0x2872ac00,0xabd9261f,0x223e29a8,0x2aa7ab64,0xaaa72c00,0x223e261f,0x2bd9a9a8,0x2872ab64,
0x2bd9ac00,0x2aa7ab64,0x2872a9a8,0x223ea61f,0x223e0000,0x2872a61f,0x2aa7a9a8,0x2bd9ab64,0xa8720000,0xabd92b64,0xa23e29a8,0x2aa7a61f,
0x2aa70000,0x223eab64,0xabd929a8,0x2872261f,0xabd90000,0x2aa7261f,0xa872a9a8,0x223e2b64,0x2bd90000,0xaaa7261f,0x2872a9a8,0xa23e2b64,
0xaaa70000,0xa23eab64,0x2bd929a8,0xa872261f,0x28720000,0x2bd92b64,0x223e29a8,0xaaa7a61f,0xa23e0000,0xa872a61f,0xaaa7a9a8,0xabd9ab64,
0xabd92c00,0xaaa72b64,0xa87229a8,0xa23e261f,0x2aa7ac00,0xa23ea61f,0xabd929a8,0xa8722b64,0xa8722c00,0x2bd9a61f,0xa23ea9a8,0xaaa72b64,
0x223eac00,0xa8722b64,0x2aa7a9a8,0xabd9261f,0x223e2c00,0xa872ab64,0x2aa729a8,0xabd9a61f,0xa872ac00,0x2bd9261f,0xa23e29a8,0xaaa7ab64,
0x2aa72c00,0xa23e261f,0xabd9a9a8,0xa872ab64,0xabd9ac00,0xaaa7ab64,0xa872a9a8,0xa23ea61f,0xabd9ac00,0xaaa7ab64,0xa872a9a8,0xa23ea61f,
0x2aa72c00,0xa23e261f,0xabd9a9a8,0xa872ab64,0xa872ac00,0x2bd9261f,0xa23e29a8,0xaaa7ab64,0x223e2c00,0xa872ab64,0x2aa729a8,0xabd9a61f,
0x223eac00,0xa8722b64,0x2aa7a9a8,0xabd9261f,0xa8722c00,0x2bd9a61f,0xa23ea9a8,0xaaa72b64,0x2aa7ac00,0xa23ea61f,0xabd929a8,0xa8722b64,
0xabd92c00,0xaaa72b64,0xa87229a8,0xa23e261f,0xa23e0000,0xa872a61f,0xaaa7a9a8,0xabd9ab64,0x28720000,0x2bd92b64,0x223e29a8,0xaaa7a61f,
0xaaa70000,0xa23eab64,0x2bd929a8,0xa872261f,0x2bd90000,0xaaa7261f,0x2872a9a8,0xa23e2b64,0xabd90000,0x2aa7261f,0xa872a9a8,0x223e2b64,
0x2aa70000,0x223eab64,0xabd929a8,0x2872261f,0xa8720000,0xabd92b64,0xa23e29a8,0x2aa7a61f,0x223e0000,0x2872a61f,0x2aa7a9a8,0x2bd9ab64,
0x2bd9ac00,0x2aa7ab64,0x2872a9a8,0x223ea61f,0xaaa72c00,0x223e261f,0x2bd9a9a8,0x2872ab64,0x2872ac00,0xabd9261f,0x223e29a8,0x2aa7ab64,
0xa23e2c00,0x2872ab64,0xaaa729a8,0x2bd9a61f,0xa23eac00,0x28722b64,0xaaa7a9a8,0x2bd9261f,0x28722c00,0xabd9a61f,0x223ea9a8,0x2aa72b64,
0xaaa7ac00,0x223ea61f,0x2bd929a8,0x28722b64,0x2bd92c00,0x2aa72b64,0x287229a8,0x223e261f,0x223e0000,0x2872a61f,0x2aa7a9a8,0x2bd9ab64,
0xa8720000,0xabd92b64,0xa23e29a8,0x2aa7a61f,0x2aa70000,0x223eab64,0xabd929a8,0x2872261f,0xabd90000,0x2aa7261f,0xa872a9a8,0x223e2b64,
0x2bd90000,0xaaa7261f,0x2872a9a8,0xa23e2b64,0xaaa70000,0xa23eab64,0x2bd929a8,0xa872261f,0x28720000,0x2bd92b64,0x223e29a8,0xaaa7a61f,
0xa23e0000,0xa872a61f,0xaaa7a9a8,0xabd9ab64,0x27fe2800,0x96480000,0x273b2764,0xa2d7a21f,0x27ea27f6,0x9cb29a46,0x26dd270e,0xa41da38b,
0x27c327d9,0x9fc69e3e,0x266d26a7,0xa4c4a472,0x278827a8,0xa164a0a5,0x25ed262f,0xa55fa513,0x27c32800,0x9fc60000,0xa4c4a21f,0xa66da764,
0x25ed270e,0xa55fa38b,0xa73ba62f,0xa2d7a513,0x21642472,0xa788a6a7,0xa7fea7d9,0x16489e3e,0x9cb21a46,0xa7eaa7f6,0xa6dda7a8,0x241d20a5,
0x273b2800,0xa2d70000,0xa55fa764,0x25ed221f,0x1fc62513,0xa7c3a62f,0x1cb2a0a5,0x27ea27a8,0xa4c49e3e,0xa66da7d9,0x26dd2472,0x241d26a7,
0xa7fea70e,0x9648a38b,0x278827f6,0xa1641a46,0x266d2800,0xa4c40000,0x26dd221f,0x241d2764,0xa16420a5,0xa788a7a8,0x25ed27f6,0xa55f9a46,
0xa7fea6a7,0x1648a472,0xa2d71e3e,0xa73ba7d9,0x9fc6a62f,0x27c32513,0xa7eaa70e,0x1cb2a38b,0x255f2800,0xa5ed0000,0x21642764,0xa788a21f,
0xa66d9a46,0xa4c4a7f6,0xa7c3a38b,0x9fc6a70e,0xa41da7d9,0x26dd1e3e,0x9cb2a6a7,0x27ea2472,0x273b20a5,0x22d727a8,0x27fe2513,0x1648262f,
0x241d2800,0xa6dd0000,0xa7eaa21f,0x9cb2a764,0xa7fea38b,0x9648a70e,0x2164a513,0x2788262f,0x22d7a472,0x273b26a7,0x255f27d9,0xa5ed1e3e,
0x24c427f6,0xa66d1a46,0xa7c3a0a5,0x9fc6a7a8,0x21642800,0xa7880000,0x1648a764,0x27fe221f,0xa6dda62f,0x241da513,0x24c427a8,0xa66d20a5,
0x27ea1e3e,0x1cb227d9,0xa7c3a472,0x1fc6a6a7,0xa55f238b,0xa5eda70e,0x273b9a46,0x22d727f6,0x1cb22800,0xa7ea0000,0x27c3221f,0x9fc62764,
0xa2d7a7a8,0x273ba0a5,0xa7fe9a46,0x9648a7f6,0x255f26a7,0xa5ed2472,0x27889e3e,0x216427d9,0xa6dda513,0x241da62f,0xa66d238b,0xa4c4a70e,
0x96482800,0xa7fe0000,0xa2d72764,0xa73ba21f,0x1cb2a7f6,0x27ea1a46,0x241da70e,0x26dd238b,0x9fc627d9,0xa7c39e3e,0xa4c426a7,0xa66da472,
0x2164a7a8,0x278820a5,0x255fa62f,0x25ed2513,0x9fc62800,0xa7c30000,0xa66da21f,0x24c4a764,0x255fa70e,0x25ed238b,0x22d7262f,0xa73b2513,
0xa7882472,0xa164a6a7,0x1648a7d9,0x27fe9e3e,0x27ea9a46,0x9cb227f6,0xa41d27a8,0xa6dda0a5,0xa2d72800,0xa73b0000,0x25eda764,0x255f221f,
0x27c3a513,0x1fc6262f,0xa7ea20a5,0x1cb2a7a8,0xa66d9e3e,0x24c4a7d9,0x241d2472,0xa6dd26a7,0x1648270e,0xa7fe238b,0x2164a7f6,0x27889a46,
0xa4c42800,0xa66d0000,0x241d221f,0xa6dd2764,0x2788a0a5,0xa16427a8,0x255fa7f6,0x25ed1a46,0x1648a6a7,0x27fea472,0xa73b1e3e,0x22d7a7d9,
0xa7c3262f,0x9fc6a513,0x9cb2270e,0xa7ea238b,0xa5ed2800,0xa55f0000,0xa7882764,0xa164a21f,0x24c41a46,0xa66d27f6,0x1fc6238b,0xa7c3270e,
0x26dda7d9,0x241d1e3e,0x27eaa6a7,0x1cb22472,0xa2d7a0a5,0x273ba7a8,0x9648a513,0x27fea62f,0xa6dd2800,0xa41d0000,0x9cb2a21f,0x27eaa764,
0x1648238b,0xa7fe270e,0xa7882513,0x2164a62f,0x273ba472,0xa2d726a7,0xa5ed27d9,0xa55f1e3e,0x266da7f6,0x24c49a46,0x1fc620a5,0xa7c327a8,
0xa7882800,0xa1640000,0x27fea764,0x9648221f,0xa41d262f,0xa6dd2513,0x266da7a8,0x24c4a0a5,0x1cb21e3e,0xa7ea27d9,0x1fc6a472,0x27c3a6a7,
0x25eda38b,0xa55f270e,0xa2d71a46,0x273ba7f6,0xa7ea2800,0x9cb20000,0x9fc6221f,0xa7c32764,0xa73b27a8,0xa2d720a5,0x16481a46,0xa7fe27f6,
0xa5ed26a7,0xa55f2472,0x21649e3e,0xa78827d9,0xa41d2513,0xa6dd262f,0x24c4a38b,0xa66d270e,0xa7fe2800,0x16480000,0xa73b2764,0x22d7a21f,
0xa7ea27f6,0x1cb29a46,0xa6dd270e,0x241da38b,0xa7c327d9,0x1fc69e3e,0xa66d26a7,0x24c4a472,0xa78827a8,0x2164a0a5,0xa5ed262f,0x255fa513,
0xa7c32800,0x1fc60000,0x24c4a21f,0x266da764,0xa5ed270e,0x255fa38b,0x273ba62f,0x22d7a513,0xa1642472,0x2788a6a7,0x27fea7d9,0x96489e3e,
0x1cb21a46,0x27eaa7f6,0x26dda7a8,0xa41d20a5,0xa73b2800,0x22d70000,0x255fa764,0xa5ed221f,0x9fc62513,0x27c3a62f,0x9cb2a0a5,0xa7ea27a8,
0x24c49e3e,0x266da7d9,0xa6dd2472,0xa41d26a7,0x27fea70e,0x1648a38b,0xa78827f6,0x21641a46,0xa66d2800,0x24c40000,0xa6dd221f,0xa41d2764,
0x216420a5,0x2788a7a8,0xa5ed27f6,0x255f9a46,0x27fea6a7,0x9648a472,0x22d71e3e,0x273ba7d9,0x1fc6a62f,0xa7c32513,0x27eaa70e,0x9cb2a38b,
0xa55f2800,0x25ed0000,0xa1642764,0x2788a21f,0x266d9a46,0x24c4a7f6,0x27c3a38b,0x1fc6a70e,0x241da7d9,0xa6dd1e3e,0x1cb2a6a7,0xa7ea2472,
0xa73b20a5,0xa2d727a8,0xa7fe2513,0x9648262f,0xa41d2800,0x26dd0000,0x27eaa21f,0x1cb2a764,0x27fea38b,0x1648a70e,0xa164a513,0xa788262f,
0xa2d7a472,0xa73b26a7,0xa55f27d9,0x25ed1e3e,0xa4c427f6,0x266d1a46,0x27c3a0a5,0x1fc6a7a8,0xa1642800,0x27880000,0x9648a764,0xa7fe221f,
0x26dda62f,0xa41da513,0xa4c427a8,0x266d20a5,0xa7ea1e3e,0x9cb227d9,0x27c3a472,0x9fc6a6a7,0x255f238b,0x25eda70e,0xa73b9a46,0xa2d727f6,
0x9cb22800,0x27ea0000,0xa7c3221f,0x1fc62764,0x22d7a7a8,0xa73ba0a5,0x27fe9a46,0x1648a7f6,0xa55f26a7,0x25ed2472,0xa7889e3e,0xa16427d9,
0x26dda513,0xa41da62f,0x266d238b,0x24c4a70e,0x16482800,0x27fe0000,0x22d72764,0x273ba21f,0x9cb2a7f6,0xa7ea1a46,0xa41da70e,0xa6dd238b,
0x1fc627d9,0x27c39e3e,0x24c426a7,0x266da472,0xa164a7a8,0xa78820a5,0xa55fa62f,0xa5ed2513,0x1fc62800,0x27c30000,0x266da21f,0xa4c4a764,
0xa55fa70e,0xa5ed238b,0xa2d7262f,0x273b2513,0x27882472,0x2164a6a7,0x9648a7d9,0xa7fe9e3e,0xa7ea9a46,0x1cb227f6,0x241d27a8,0x26dda0a5,
0x22d72800,0x273b0000,0xa5eda764,0xa55f221f,0xa7c3a513,0x9fc6262f,0x27ea20a5,0x9cb2a7a8,0x266d9e3e,0xa4c4a7d9,0xa41d2472,0x26dd26a7,
0x9648270e,0x27fe238b,0xa164a7f6,0xa7889a46,0x24c42800,0x266d0000,0xa41d221f,0x26dd2764,0xa788a0a5,0x216427a8,0xa55fa7f6,0xa5ed1a46,
0x9648a6a7,0xa7fea472,0x273b1e3e,0xa2d7a7d9,0x27c3262f,0x1fc6a513,0x1cb2270e,0x27ea238b,0x25ed2800,0x255f0000,0x27882764,0x2164a21f,
0xa4c41a46,0x266d27f6,0x9fc6238b,0x27c3270e,0xa6dda7d9,0xa41d1e3e,0xa7eaa6a7,0x9cb22472,0x22d7a0a5,0xa73ba7a8,0x1648a513,0xa7fea62f,
0x26dd2800,0x241d0000,0x1cb2a21f,0xa7eaa764,0x9648238b,0x27fe270e,0x27882513,0xa164a62f,0xa73ba472,0x22d726a7,0x25ed27d9,0x255f1e3e,
0xa66da7f6,0xa4c49a46,0x9fc620a5,0x27c327a8,0x27882800,0x21640000,0xa7fea764,0x1648221f,0x241d262f,0x26dd2513,0xa66da7a8,0xa4c4a0a5,
0x9cb21e3e,0x27ea27d9,0x9fc6a472,0xa7c3a6a7,0xa5eda38b,0x255f270e,0x22d71a46,0xa73ba7f6,0x27ea2800,0x1cb20000,0x1fc6221f,0x27c32764,
0x273b27a8,0x22d720a5,0x96481a46,0x27fe27f6,0x25ed26a7,0x255f2472,0xa1649e3e,0x278827d9,0x241d2513,0x26dd262f,0xa4c4a38b,0x266d270e,
0x255f25a8,0xa5eda5a8,0x2164221f,0xa788a764,0x24c42513,0xa66da62f,0x1fc620a5,0xa7c3a7a8,0x241d2472,0xa6dda6a7,0x1cb21e3e,0xa7eaa7d9,
0x22d7238b,0xa73ba70e,0x16481a46,0xa7fea7f6,0xa41da5a8,0x26dd25a8,0x27ea2764,0x1cb2221f,0x9648a0a5,0x27fe27a8,0x278827f6,0xa1649a46,
0x22d71e3e,0x273b27d9,0x255f26a7,0xa5eda472,0x266d2513,0x24c4262f,0x1fc6238b,0xa7c3a70e,0x216425a8,0xa788a5a8,0x1648a21f,0x27fe2764,
0xa41d9a46,0xa6dda7f6,0x266d238b,0x24c4270e,0xa7eaa6a7,0x9cb2a472,0x27c327d9,0x9fc61e3e,0xa5eda7a8,0x255f20a5,0x22d7262f,0xa73ba513,
0x9cb2a5a8,0x27ea25a8,0xa7c3a764,0x1fc6a21f,0x273b238b,0x22d7270e,0x9648a513,0x27fe262f,0x255f27d9,0xa5ed9e3e,0x27882472,0x216426a7,
0xa41d1a46,0xa6dda7f6,0x24c427a8,0xa66da0a5,0x964825a8,0xa7fea5a8,0xa2d7221f,0xa73ba764,0xa7eaa62f,0x1cb2a513,0xa6dda7a8,0x241da0a5,
0x1fc6a472,0x27c326a7,0x24c49e3e,0x266d27d9,0x2788270e,0xa164238b,0x25ed27f6,0xa55f1a46,0x1fc6a5a8,0x27c325a8,0x266d2764,0xa4c4221f,
0x25ed27a8,0xa55f20a5,0xa73b9a46,0xa2d7a7f6,0xa7889e3e,0xa164a7d9,0x1648a6a7,0x27fe2472,0x1cb2a62f,0x27ea2513,0x26dd270e,0xa41d238b,
0xa2d725a8,0xa73ba5a8,0x25eda21f,0x255f2764,0x9fc6a7f6,0x27c31a46,0x9cb2270e,0xa7eaa38b,0x266d26a7,0xa4c42472,0xa41da7d9,0x26dd9e3e,
0xa7fea0a5,0x9648a7a8,0x27882513,0xa164262f,0x24c4a5a8,0x266d25a8,0xa41da764,0x26dda21f,0xa164270e,0xa788a38b,0x25ed262f,0xa55f2513,
0x1648a7d9,0x27fe1e3e,0xa73ba472,0x22d7a6a7,0x1fc627f6,0xa7c31a46,0x27ea20a5,0x9cb227a8,0xa5ed25a8,0xa55fa5a8,0xa788221f,0xa164a764,
0x266da513,0x24c4262f,0x27c3a0a5,0x1fc627a8,0xa6dd2472,0xa41da6a7,0xa7ea1e3e,0x9cb2a7d9,0x273ba38b,0x22d7270e,0x27fe9a46,0x164827f6,
0x26dda5a8,0x241d25a8,0x1cb22764,0xa7ea221f,0xa7fe20a5,0x9648a7a8,0x2164a7f6,0x27881a46,0x273b1e3e,0xa2d727d9,0xa5ed26a7,0xa55fa472,
0xa4c4a513,0x266da62f,0x27c3a38b,0x1fc6270e,0xa78825a8,0xa164a5a8,0x27fea21f,0x96482764,0x26dd1a46,0xa41d27f6,0xa4c4a38b,0x266da70e,
0x9cb2a6a7,0x27eaa472,0x9fc627d9,0xa7c31e3e,0xa55f27a8,0xa5eda0a5,0x273ba62f,0x22d72513,0x27eaa5a8,0x1cb225a8,0x1fc6a764,0x27c3a21f,
0xa2d7a38b,0x273ba70e,0xa7fe2513,0x9648a62f,0xa5ed27d9,0xa55f9e3e,0x21642472,0xa78826a7,0x26dd9a46,0xa41d27f6,0x266da7a8,0x24c420a5,
0xa7fe25a8,0x1648a5a8,0xa73b221f,0x22d7a764,0x9cb2262f,0xa7ea2513,0xa41d27a8,0xa6dd20a5,0x27c3a472,0x9fc626a7,0x266d9e3e,0xa4c427d9,
0x2164a70e,0x2788a38b,0x255fa7f6,0x25ed9a46,0x27c3a5a8,0x9fc625a8,0xa4c42764,0xa66d221f,0x255fa7a8,0x25eda0a5,0x22d71a46,0xa73b27f6,
0xa1649e3e,0x2788a7d9,0x27fea6a7,0x96482472,0xa7ea262f,0x1cb2a513,0x241da70e,0x26dda38b,0xa73b25a8,0x22d7a5a8,0x255fa21f,0xa5ed2764,
0xa7c327f6,0x9fc69a46,0x27eaa70e,0x9cb2238b,0xa4c426a7,0xa66d2472,0x26dda7d9,0x241d9e3e,0x164820a5,0xa7fe27a8,0x2164a513,0x2788a62f,
0x266da5a8,0xa4c425a8,0x26dda764,0x241da21f,0x2788a70e,0xa164238b,0x255fa62f,0x25eda513,0x27fea7d9,0x96481e3e,0x22d7a472,0x273ba6a7,
0x27c3a7f6,0x1fc69a46,0x1cb2a0a5,0x27eaa7a8,0xa55f25a8,0x25eda5a8,0xa164221f,0x2788a764,0xa4c42513,0x266da62f,0x9fc620a5,0x27c3a7a8,
0xa41d2472,0x26dda6a7,0x9cb21e3e,0x27eaa7d9,0xa2d7238b,0x273ba70e,0x96481a46,0x27fea7f6,0x241da5a8,0xa6dd25a8,0xa7ea2764,0x9cb2221f,
0x1648a0a5,0xa7fe27a8,0xa78827f6,0x21649a46,0xa2d71e3e,0xa73b27d9,0xa55f26a7,0x25eda472,0xa66d2513,0xa4c4262f,0x9fc6238b,0x27c3a70e,
0xa16425a8,0x2788a5a8,0x9648a21f,0xa7fe2764,0x241d9a46,0x26dda7f6,0xa66d238b,0xa4c4270e,0x27eaa6a7,0x1cb2a472,0xa7c327d9,0x1fc61e3e,
0x25eda7a8,0xa55f20a5,0xa2d7262f,0x273ba513,0x1cb2a5a8,0xa7ea25a8,0x27c3a764,0x9fc6a21f,0xa73b238b,0xa2d7270e,0x1648a513,0xa7fe262f,
0xa55f27d9,0x25ed9e3e,0xa7882472,0xa16426a7,0x241d1a46,0x26dda7f6,0xa4c427a8,0x266da0a5,0x164825a8,0x27fea5a8,0x22d7221f,0x273ba764,
0x27eaa62f,0x9cb2a513,0x26dda7a8,0xa41da0a5,0x9fc6a472,0xa7c326a7,0xa4c49e3e,0xa66d27d9,0xa788270e,0x2164238b,0xa5ed27f6,0x255f1a46,
0x9fc6a5a8,0xa7c325a8,0xa66d2764,0x24c4221f,0xa5ed27a8,0x255f20a5,0x273b9a46,0x22d7a7f6,0x27889e3e,0x2164a7d9,0x9648a6a7,0xa7fe2472,
0x9cb2a62f,0xa7ea2513,0xa6dd270e,0x241d238b,0x22d725a8,0x273ba5a8,0xa5eda21f,0xa55f2764,0x1fc6a7f6,0xa7c31a46,0x1cb2270e,0x27eaa38b,
0xa66d26a7,0x24c42472,0x241da7d9,0xa6dd9e3e,0x27fea0a5,0x1648a7a8,0xa7882513,0x2164262f,0xa4c4a5a8,0xa66d25a8,0x241da764,0xa6dda21f,
0x2164270e,0x2788a38b,0xa5ed262f,0x255f2513,0x9648a7d9,0xa7fe1e3e,0x273ba472,0xa2d7a6a7,0x9fc627f6,0x27c31a46,0xa7ea20a5,0x1cb227a8,
0x25ed25a8,0x255fa5a8,0x2788221f,0x2164a764,0xa66da513,0xa4c4262f,0xa7c3a0a5,0x9fc627a8,0x26dd2472,0x241da6a7,0x27ea1e3e,0x1cb2a7d9,
0xa73ba38b,0xa2d7270e,0xa7fe9a46,0x964827f6,0xa6dda5a8,0xa41d25a8,0x9cb22764,0x27ea221f,0x27fe20a5,0x1648a7a8,0xa164a7f6,0xa7881a46,
0xa73b1e3e,0x22d727d9,0x25ed26a7,0x255fa472,0x24c4a513,0xa66da62f,0xa7c3a38b,0x9fc6270e,0x278825a8,0x2164a5a8,0xa7fea21f,0x16482764,
0xa6dd1a46,0x241d27f6,0x24c4a38b,0xa66da70e,0x1cb2a6a7,0xa7eaa472,0x1fc627d9,0x27c31e3e,0x255f27a8,0x25eda0a5,0xa73ba62f,0xa2d72513,
0xa7eaa5a8,0x9cb225a8,0x9fc6a764,0xa7c3a21f,0x22d7a38b,0xa73ba70e,0x27fe2513,0x1648a62f,0x25ed27d9,0x255f9e3e,0xa1642472,0x278826a7,
0xa6dd9a46,0x241d27f6,0xa66da7a8,0xa4c420a5,0x27fe25a8,0x9648a5a8,0x273b221f,0xa2d7a764,0x1cb2262f,0x27ea2513,0x241d27a8,0x26dd20a5,
0xa7c3a472,0x1fc626a7,0xa66d9e3e,0x24c427d9,0xa164a70e,0xa788a38b,0xa55fa7f6,0xa5ed9a46,0xa7c3a5a8,0x1fc625a8,0x24c42764,0x266d221f,
0xa55fa7a8,0xa5eda0a5,0xa2d71a46,0x273b27f6,0x21649e3e,0xa788a7d9,0xa7fea6a7,0x16482472,0x27ea262f,0x9cb2a513,0xa41da70e,0xa6dda38b,
0x273b25a8,0xa2d7a5a8,0xa55fa21f,0x25ed2764,0x27c327f6,0x1fc69a46,0xa7eaa70e,0x1cb2238b,0x24c426a7,0x266d2472,0xa6dda7d9,0xa41d9e3e,
0x964820a5,0x27fe27a8,0xa164a513,0xa788a62f,0xa66da5a8,0x24c425a8,0xa6dda764,0xa41da21f,0xa788a70e,0x2164238b,0xa55fa62f,0xa5eda513,
0xa7fea7d9,0x16481e3e,0xa2d7a472,0xa73ba6a7,0xa7c3a7f6,0x9fc69a46,0x9cb2a0a5,0xa7eaa7a8,
};

#define PROF(slot) do {} while (0)
#define PROF3(slot) do {} while (0)
#define PROF2(slot) do {} while (0)

__device__ __forceinline__ uint32_t smem_u32(const void* p) { return (uint32_t)__cvta_generic_to_shared(p); }

__device__ __forceinline__ void mbar_init(uint32_t a, uint32_t c) {
  asm volatile("mbarrier.init.shared::cta.b64 [%0], %1;\n" ::"r"(a), "r"(c) : "memory");
}
__device__ __forceinline__ void mbar_expect_tx(uint32_t a, uint32_t bytes) {
  asm volatile("mbarrier.arrive.expect_tx.shared::cta.b64 _, [%0], %1;\n" ::"r"(a), "r"(bytes) : "memory");
}
__device__ __forceinline__ void mbar_arrive_cluster(uint32_t cluster_addr) {
  asm volatile("mbarrier.arrive.shared::cluster.b64 _, [%0];\n" ::"r"(cluster_addr) : "memory");
}
__device__ __forceinline__ void mbar_arrive_cluster_n(uint32_t cluster_addr, uint32_t n) {
  asm volatile("mbarrier.arrive.shared::cluster.b64 _, [%0], %1;\n" ::"r"(cluster_addr), "r"(n) : "memory");
}
__device__ __forceinline__ bool mbar_try(uint32_t a, uint32_t parity) {
  uint32_t ok;
  asm volatile("{\n.reg .pred p;\nmbarrier.try_wait.parity.shared::cta.b64 p, [%1], %2;\nselp.u32 %0, 1, 0, p;\n}\n"
               : "=r"(ok) : "r"(a), "r"(parity) : "memory");
  return ok;
}
__device__ __forceinline__ void mbar_wait(uint32_t a, uint32_t parity) {
  if (mbar_try(a, parity)) return;
#pragma unroll 1
  for (int n = 0; n < SPIN_LIMIT; n++)
    if (mbar_try(a, parity)) break;
}
__device__ __forceinline__ void mbar_wait_idle(uint32_t a, uint32_t parity) {
#pragma unroll 1
  for (int n = 0; n < SPIN_LIMIT; n++) {
    uint32_t ok;
    asm volatile("{\n.reg .pred p;\nmbarrier.try_wait.parity.shared::cta.b64 p, [%1], %2, %3;\nselp.u32 %0, 1, 0, p;\n}\n"
                 : "=r"(ok) : "r"(a), "r"(parity), "r"(4000) : "memory");
    if (ok) break;
  }
}
__device__ __forceinline__ bool elect_one() {
  uint32_t p;
  asm volatile("{\n.reg .pred P;\nelect.sync _|P, 0xffffffff;\nselp.u32 %0, 1, 0, P;\n}\n" : "=r"(p));
  return p;
}
__device__ __forceinline__ uint32_t mapa(uint32_t a, uint32_t rank) {
  uint32_t r;
  asm volatile("mapa.shared::cluster.u32 %0, %1, %2;\n" : "=r"(r) : "r"(a), "r"(rank));
  return r;
}
__device__ __forceinline__ void nb_sync(int id, int n) { asm volatile("bar.sync %0, %1;\n" ::"r"(id), "r"(n) : "memory"); }
__device__ __forceinline__ void nb_arrive(int id, int n) { asm volatile("bar.arrive %0, %1;\n" ::"r"(id), "r"(n) : "memory"); }
__device__ __forceinline__ void cluster_sync_all() {
  asm volatile("barrier.cluster.arrive.relaxed.aligned;\nbarrier.cluster.wait.aligned;\n" ::: "memory");
}
__device__ __forceinline__ void fence_async_smem() { asm volatile("fence.proxy.async.shared::cta;\n" ::: "memory"); }
__device__ __forceinline__ void fence_async_all() { asm volatile("fence.proxy.async.global;\n" ::: "memory"); }

__device__ __forceinline__ void tma_load_3d(uint32_t dst, const CUtensorMap* tm, uint32_t bar, int c0, int c1, int c2) {
  asm volatile(
      "cp.async.bulk.tensor.3d.shared::cluster.global.mbarrier::complete_tx::bytes [%0], [%1, {%3, %4, %5}], [%2];\n"
      ::"r"(dst), "l"(tm), "r"(bar), "r"(c0), "r"(c1), "r"(c2) : "memory");
}
__device__ __forceinline__ void tma_load_4d(uint32_t dst, const CUtensorMap* tm, uint32_t bar, int c0, int c1, int c2, int c3) {
  asm volatile(
      "cp.async.bulk.tensor.4d.shared::cluster.global.mbarrier::complete_tx::bytes [%0], [%1, {%3, %4, %5, %6}], [%2];\n"
      ::"r"(dst), "l"(tm), "r"(bar), "r"(c0), "r"(c1), "r"(c2), "r"(c3) : "memory");
}
__device__ __forceinline__ void tma_load_3d_mc(uint32_t dst, const CUtensorMap* tm, uint32_t bar, int c0, int c1, int c2) {
  asm volatile(
      "cp.async.bulk.tensor.3d.shared::cluster.global.mbarrier::complete_tx::bytes.multicast::cluster [%0], [%1, {%3, %4, %5}], [%2], %6;\n"
      ::"r"(dst), "l"(tm), "r"(bar), "r"(c0), "r"(c1), "r"(c2), "h"((uint16_t)3) : "memory");
}
__device__ __forceinline__ void tma_load_5d(uint32_t dst, const CUtensorMap* tm, uint32_t bar, int c0, int c4) {
  asm volatile(
      "cp.async.bulk.tensor.5d.shared::cluster.global.mbarrier::complete_tx::bytes [%0], [%1, {%3, %5, %5, %5, %4}], [%2];\n"
      ::"r"(dst), "l"(tm), "r"(bar), "r"(c0), "r"(c4), "r"(0) : "memory");
}
__device__ __forceinline__ void bulk_load(uint32_t dst, const void* src, uint32_t bytes, uint32_t bar) {
  asm volatile("cp.async.bulk.shared::cluster.global.mbarrier::complete_tx::bytes [%0], [%1], %2, [%3];\n"
               ::"r"(dst), "l"(src), "r"(bytes), "r"(bar) : "memory");
}
__device__ __forceinline__ void bulk_commit() { asm volatile("cp.async.bulk.commit_group;\n" ::: "memory"); }
__device__ __forceinline__ void bulk_wait0() { asm volatile("cp.async.bulk.wait_group 0;\n" ::: "memory"); }
__device__ __forceinline__ void prefetch_tmap(const CUtensorMap* tm) {
  asm volatile("prefetch.tensormap [%0];\n" ::"l"(tm) : "memory");
}

__device__ __forceinline__ void wg_fence() { asm volatile("wgmma.fence.sync.aligned;\n" ::: "memory"); }
__device__ __forceinline__ void wg_commit() { asm volatile("wgmma.commit_group.sync.aligned;\n" ::: "memory"); }
template <int N> __device__ __forceinline__ void wg_wait() {
  asm volatile("wgmma.wait_group.sync.aligned %0;\n" ::"n"(N) : "memory");
}
__device__ __forceinline__ uint64_t mkdesc(uint32_t addr, uint32_t lbo, uint32_t sbo, uint32_t swz) {
  return (uint64_t)((addr & 0x3FFFF) >> 4) | ((uint64_t)(lbo >> 4) << 16) | ((uint64_t)(sbo >> 4) << 32) |
         ((uint64_t)swz << 62);
}

#define R4(d, o) "+f"(d[o + 0]), "+f"(d[o + 1]), "+f"(d[o + 2]), "+f"(d[o + 3])
#define R8(d, o) R4(d, o), R4(d, o + 4)
#define R16(d, o) R8(d, o), R8(d, o + 8)
#define R32(d, o) R16(d, o), R16(d, o + 16)
#define R64(d, o) R32(d, o), R32(d, o + 32)

__device__ __forceinline__ void wgmma_n192(float (&d)[96], uint64_t da, uint64_t db, uint32_t acc) {
  asm volatile(
      "{\n.reg .pred p;\nsetp.ne.u32 p, %98, 0;\n"
      "wgmma.mma_async.sync.aligned.m64n192k16.f32.bf16.bf16 "
      "{%0,%1,%2,%3,%4,%5,%6,%7,%8,%9,%10,%11,%12,%13,%14,%15,%16,%17,%18,%19,%20,%21,%22,%23,%24,%25,%26,%27,%28,%29,%30,%31,"
      "%32,%33,%34,%35,%36,%37,%38,%39,%40,%41,%42,%43,%44,%45,%46,%47,%48,%49,%50,%51,%52,%53,%54,%55,%56,%57,%58,%59,%60,%61,%62,%63,"
      "%64,%65,%66,%67,%68,%69,%70,%71,%72,%73,%74,%75,%76,%77,%78,%79,%80,%81,%82,%83,%84,%85,%86,%87,%88,%89,%90,%91,%92,%93,%94,%95}, "
      "%96, %97, p, 1, 1, 0, 1;\n}\n"
      : R64(d, 0), R32(d, 64)
      : "l"(da), "l"(db), "r"(acc));
}
__device__ __forceinline__ void wgmma_n128(float (&d)[64], uint64_t da, uint64_t db, uint32_t acc) {
  asm volatile(
      "{\n.reg .pred p;\nsetp.ne.u32 p, %66, 0;\n"
      "wgmma.mma_async.sync.aligned.m64n128k16.f32.bf16.bf16 "
      "{%0,%1,%2,%3,%4,%5,%6,%7,%8,%9,%10,%11,%12,%13,%14,%15,%16,%17,%18,%19,%20,%21,%22,%23,%24,%25,%26,%27,%28,%29,%30,%31,"
      "%32,%33,%34,%35,%36,%37,%38,%39,%40,%41,%42,%43,%44,%45,%46,%47,%48,%49,%50,%51,%52,%53,%54,%55,%56,%57,%58,%59,%60,%61,%62,%63}, "
      "%64, %65, p, 1, 1, 0, 1;\n}\n"
      : R64(d, 0)
      : "l"(da), "l"(db), "r"(acc));
}
template <int N> __device__ __forceinline__ void fence_regs(float (&d)[N]) {
#pragma unroll
  for (int i = 0; i < N; i++) asm volatile("" : "+f"(d[i])::"memory");
}

__device__ __forceinline__ void mma16816(float (&d)[4], uint32_t a0, uint32_t a1, uint32_t a2, uint32_t a3, uint32_t b0,
                                         uint32_t b1) {
  asm("mma.sync.aligned.m16n8k16.row.col.f32.bf16.bf16.f32 {%0,%1,%2,%3}, {%4,%5,%6,%7}, {%8,%9}, {%0,%1,%2,%3};\n"
      : "+f"(d[0]), "+f"(d[1]), "+f"(d[2]), "+f"(d[3])
      : "r"(a0), "r"(a1), "r"(a2), "r"(a3), "r"(b0), "r"(b1));
}
__device__ __forceinline__ void mma16816_z(float (&d)[4], uint32_t a0, uint32_t a1, uint32_t a2, uint32_t a3, uint32_t b0,
                                           uint32_t b1) {
  asm("mma.sync.aligned.m16n8k16.row.col.f32.bf16.bf16.f32 {%0,%1,%2,%3}, {%4,%5,%6,%7}, {%8,%9}, {%10,%10,%10,%10};\n"
      : "=f"(d[0]), "=f"(d[1]), "=f"(d[2]), "=f"(d[3])
      : "r"(a0), "r"(a1), "r"(a2), "r"(a3), "r"(b0), "r"(b1), "f"(0.f));
}
__device__ __forceinline__ void ldsm4t(uint32_t (&r)[4], uint32_t a) {
  asm volatile("ldmatrix.sync.aligned.m8n8.x4.trans.shared.b16 {%0,%1,%2,%3}, [%4];\n"
               : "=r"(r[0]), "=r"(r[1]), "=r"(r[2]), "=r"(r[3]) : "r"(a) : "memory");
}
__device__ __forceinline__ void ldsm2t(uint32_t& r0, uint32_t& r1, uint32_t a) {
  asm volatile("ldmatrix.sync.aligned.m8n8.x2.trans.shared.b16 {%0,%1}, [%2];\n" : "=r"(r0), "=r"(r1) : "r"(a) : "memory");
}
__device__ __forceinline__ void st_async128(uint32_t a, uint32_t bar, uint32_t x, uint32_t y, uint32_t z, uint32_t w) {
  asm volatile("st.async.weak.shared::cluster.mbarrier::complete_tx::bytes.v4.b32 [%0], {%2,%3,%4,%5}, [%1];\n"
               ::"r"(a), "r"(bar), "r"(x), "r"(y), "r"(z), "r"(w) : "memory");
}
__device__ __forceinline__ void mbar_arrive(uint32_t a) {
  asm volatile("mbarrier.arrive.shared::cta.b64 _, [%0];\n" ::"r"(a) : "memory");
}
__device__ __forceinline__ void stsm4(uint32_t a, uint32_t r0, uint32_t r1, uint32_t r2, uint32_t r3) {
  asm volatile("stmatrix.sync.aligned.m8n8.x4.shared.b16 [%0], {%1,%2,%3,%4};\n"
               ::"r"(a), "r"(r0), "r"(r1), "r"(r2), "r"(r3) : "memory");
}
__device__ __forceinline__ void stsm4t(uint32_t a, uint32_t r0, uint32_t r1, uint32_t r2, uint32_t r3) {
  asm volatile("stmatrix.sync.aligned.m8n8.x4.trans.shared.b16 [%0], {%1,%2,%3,%4};\n"
               ::"r"(a), "r"(r0), "r"(r1), "r"(r2), "r"(r3) : "memory");
}
__device__ __forceinline__ uint2 lds64(uint32_t a) {
  uint2 v;
  asm volatile("ld.shared.v2.u32 {%0,%1}, [%2];\n" : "=r"(v.x), "=r"(v.y) : "r"(a));
  return v;
}
__device__ __forceinline__ uint4 lds128(uint32_t a) {
  uint4 v;
  asm volatile("ld.shared.v4.u32 {%0,%1,%2,%3}, [%4];\n" : "=r"(v.x), "=r"(v.y), "=r"(v.z), "=r"(v.w) : "r"(a) : "memory");
  return v;
}
__device__ __forceinline__ void sts128(uint32_t a, uint32_t x, uint32_t y, uint32_t z, uint32_t w) {
  asm volatile("st.shared.v4.u32 [%0], {%1,%2,%3,%4};\n" ::"r"(a), "r"(x), "r"(y), "r"(z), "r"(w) : "memory");
}
__device__ __forceinline__ uint32_t pack_bf16(float lo, float hi) {
  uint32_t r;
  asm("cvt.rn.bf16x2.f32 %0, %1, %2;\n" : "=r"(r) : "f"(hi), "f"(lo));
  return r;
}
__device__ __forceinline__ uint32_t bmul2(uint32_t a, uint32_t b) {
  uint32_t r;
  asm("mul.rn.bf16x2 %0, %1, %2;\n" : "=r"(r) : "r"(a), "r"(b));
  return r;
}
__device__ __forceinline__ uint32_t bmax2(uint32_t a, uint32_t b) {
  uint32_t r;
  asm("max.bf16x2 %0, %1, %2;\n" : "=r"(r) : "r"(a), "r"(b));
  return r;
}
__device__ __forceinline__ uint32_t bfma2(uint32_t a, uint32_t b, uint32_t c) {
  uint32_t r;
  asm("fma.rn.bf16x2 %0, %1, %2, %3;\n" : "=r"(r) : "r"(a), "r"(b), "r"(c));
  return r;
}
__device__ __forceinline__ uint32_t badd2(uint32_t a, uint32_t b) {
  uint32_t r;
  asm("add.rn.bf16x2 %0, %1, %2;\n" : "=r"(r) : "r"(a), "r"(b));
  return r;
}
__device__ __forceinline__ void prefetch_l2(const void* p) { asm volatile("prefetch.global.L2 [%0];\n" ::"l"(p)); }
__device__ __forceinline__ void cp_async16n(uint32_t dst, const void* src) {
  asm volatile("cp.async.cg.shared.global [%0], [%1], 16;\n" ::"r"(dst), "l"(src) : "memory");
}
__device__ __forceinline__ void cp_async16(uint32_t dst, const void* src, uint32_t srcbytes) {
  asm volatile("cp.async.cg.shared.global.L2::256B [%0], [%1], 16, %2;\n" ::"r"(dst), "l"(src), "r"(srcbytes) : "memory");
}
__device__ __forceinline__ uint32_t ld_acquire(const uint32_t* p) {
  uint32_t v;
  asm volatile("ld.acquire.gpu.global.u32 %0, [%1];\n" : "=r"(v) : "l"(p) : "memory");
  return v;
}
__device__ __forceinline__ uint32_t ld_relaxed(const uint32_t* p) {
  uint32_t v;
  asm volatile("ld.relaxed.gpu.global.u32 %0, [%1];\n" : "=r"(v) : "l"(p) : "memory");
  return v;
}
__device__ __forceinline__ void st_release(uint32_t* p, uint32_t v) {
  asm volatile("st.release.gpu.global.u32 [%0], %1;\n" ::"l"(p), "r"(v) : "memory");
}
__device__ __forceinline__ void wait_flag(const uint32_t* p, uint32_t want) {
  int n = 0;
  while (ld_relaxed(p) != want && ++n < SPIN_LIMIT) __nanosleep(40);
  (void)ld_acquire(p);
}

struct Params {
  const __nv_bfloat16* x;
  const __nv_bfloat16* w;
  const __nv_bfloat16* q;
  const __nv_bfloat16* k;
  const __nv_bfloat16* v;
  const __nv_bfloat16* shift_k;
  const __nv_bfloat16* ssm_k;
  const __nv_bfloat16* ssm_D;
  const __nv_bfloat16* wo;
  __nv_bfloat16* out;
};

__device__ __forceinline__ uint32_t lds32(uint32_t a) {
  uint32_t v;
  asm volatile("ld.shared.u32 %0, [%1];\n" : "=r"(v) : "r"(a));
  return v;
}
#define W4(d, o) "=f"(d[o + 0]), "=f"(d[o + 1]), "=f"(d[o + 2]), "=f"(d[o + 3])
#define W8(d, o) W4(d, o), W4(d, o + 4)
#define W16(d, o) W8(d, o), W8(d, o + 8)
#define U4(c, d, o) c(d[o + 0]), c(d[o + 1]), c(d[o + 2]), c(d[o + 3])
#define U8(c, d, o) U4(c, d, o), U4(c, d, o + 4)
#define U16(c, d, o) U8(c, d, o), U8(c, d, o + 8)
#define U32(c, d, o) U16(c, d, o), U16(c, d, o + 16)
#define D32 "{%0,%1,%2,%3,%4,%5,%6,%7,%8,%9,%10,%11,%12,%13,%14,%15,%16,%17,%18,%19,%20,%21,%22,%23,%24,%25,%26,%27,%28,%29,%30,%31}"
#define D16 "{%0,%1,%2,%3,%4,%5,%6,%7,%8,%9,%10,%11,%12,%13,%14,%15}"
#define D8 "{%0,%1,%2,%3,%4,%5,%6,%7}"
template <int ACC> __device__ __forceinline__ void hmma_n128t(uint32_t (&d)[32], const uint32_t (&a)[4], uint64_t db) {
  if (ACC)
    asm volatile("wgmma.mma_async.sync.aligned.m64n128k16.f16.f16.f16 " D32 ", {%32,%33,%34,%35}, %36, 1, 1, 1, 1;\n"
                 : U32("+r", d, 0) : "r"(a[0]), "r"(a[1]), "r"(a[2]), "r"(a[3]), "l"(db));
  else
    asm volatile("wgmma.mma_async.sync.aligned.m64n128k16.f16.f16.f16 " D32 ", {%32,%33,%34,%35}, %36, 0, 1, 1, 1;\n"
                 : U32("=r", d, 0) : "r"(a[0]), "r"(a[1]), "r"(a[2]), "r"(a[3]), "l"(db));
}
template <int ACC, int TB> __device__ __forceinline__ void hmma_n32(uint32_t (&d)[8], const uint32_t (&a)[4], uint64_t db) {
  if (ACC)
    asm volatile("wgmma.mma_async.sync.aligned.m64n32k16.f16.f16.f16 " D8 ", {%8,%9,%10,%11}, %12, 1, 1, 1, %13;\n"
                 : U8("+r", d, 0) : "r"(a[0]), "r"(a[1]), "r"(a[2]), "r"(a[3]), "l"(db), "n"(TB));
  else
    asm volatile("wgmma.mma_async.sync.aligned.m64n32k16.f16.f16.f16 " D8 ", {%8,%9,%10,%11}, %12, 0, 1, 1, %13;\n"
                 : U8("=r", d, 0) : "r"(a[0]), "r"(a[1]), "r"(a[2]), "r"(a[3]), "l"(db), "n"(TB));
}
template <int ACC> __device__ __forceinline__ void hmma_n64t(uint32_t (&d)[16], const uint32_t (&a)[4], uint64_t db) {
  if (ACC)
    asm volatile("wgmma.mma_async.sync.aligned.m64n64k16.f16.f16.f16 " D16 ", {%16,%17,%18,%19}, %20, 1, 1, 1, 1;\n"
                 : U16("+r", d, 0) : "r"(a[0]), "r"(a[1]), "r"(a[2]), "r"(a[3]), "l"(db));
  else
    asm volatile("wgmma.mma_async.sync.aligned.m64n64k16.f16.f16.f16 " D16 ", {%16,%17,%18,%19}, %20, 0, 1, 1, 1;\n"
                 : U16("=r", d, 0) : "r"(a[0]), "r"(a[1]), "r"(a[2]), "r"(a[3]), "l"(db));
}
template <int N> __device__ __forceinline__ void fence_regs(uint32_t (&d)[N]) {
#pragma unroll
  for (int i = 0; i < N; i++) asm volatile("" : "+r"(d[i])::"memory");
}
__device__ __forceinline__ uint32_t hmul(uint32_t a, uint32_t b) { uint32_t r; asm("mul.rn.f16x2 %0, %1, %2;\n" : "=r"(r) : "r"(a), "r"(b)); return r; }
__device__ __forceinline__ uint32_t hadd(uint32_t a, uint32_t b) { uint32_t r; asm("add.rn.f16x2 %0, %1, %2;\n" : "=r"(r) : "r"(a), "r"(b)); return r; }
__device__ __forceinline__ uint32_t hsub(uint32_t a, uint32_t b) { uint32_t r; asm("sub.rn.f16x2 %0, %1, %2;\n" : "=r"(r) : "r"(a), "r"(b)); return r; }
__device__ __forceinline__ uint32_t hfma(uint32_t a, uint32_t b, uint32_t c) { uint32_t r; asm("fma.rn.f16x2 %0, %1, %2, %3;\n" : "=r"(r) : "r"(a), "r"(b), "r"(c)); return r; }
__device__ __forceinline__ uint32_t hfnma(uint32_t a, uint32_t b, uint32_t c) {
  uint32_t r;
  asm("{\n.reg .b32 t;\nneg.f16x2 t, %1;\nfma.rn.f16x2 %0, t, %2, %3;\n}\n" : "=r"(r) : "r"(a), "r"(b), "r"(c));
  return r;
}
__device__ __forceinline__ uint32_t hrefl(uint32_t p, uint32_t s) {
  uint32_t r;
  asm("{\n.reg .b32 t;\nneg.f16x2 t, %2;\nfma.rn.f16x2 %0, %1, %3, t;\n}\n" : "=r"(r) : "r"(p), "r"(s), "r"(0x40004000u));
  return r;
}
__device__ __forceinline__ void bfly(uint32_t xr, uint32_t xi, uint32_t tr, uint32_t ti, uint32_t yr, uint32_t yi, uint32_t ur,
                                     uint32_t ui, uint32_t& sr, uint32_t& si, uint32_t& dr, uint32_t& di) {
  const uint32_t pr = hfnma(xi, ti, hmul(xr, tr)), pi = hfma(xi, tr, hmul(xr, ti));
  sr = hfnma(yi, ui, hfma(yr, ur, pr));
  si = hfma(yi, ur, hfma(yr, ui, pi));
  dr = hrefl(pr, sr);
  di = hrefl(pi, si);
}
template <int BH> __device__ __forceinline__ void fft_e1(const uint32_t (&d)[32], const uint32_t (&tw)[16], uint32_t (&a2)[2][2][4]) {
#pragma unroll
  for (int be = 0; be < 2; be++)
#pragma unroll
    for (int s = 0; s < 2; s++) {
      const int o = 16 * s + 8 * be + 2 * BH, p = 2 * BH;
      bfly(d[o], d[o + 1], tw[p], tw[p + 1], d[o + 4], d[o + 5], tw[p + 4], tw[p + 5], a2[be][0][s], a2[be][0][2 + s],
           a2[be][1][s], a2[be][1][2 + s]);
    }
}
__device__ __forceinline__ uint32_t hfms(uint32_t a, uint32_t b, uint32_t c) {
  uint32_t r;
  asm("{\n.reg .b32 t;\nneg.f16x2 t, %3;\nfma.rn.f16x2 %0, %1, %2, t;\n}\n" : "=r"(r) : "r"(a), "r"(b), "r"(c));
  return r;
}
template <int C, int J> __device__ __forceinline__ void fft_e2(const uint32_t (&d0)[8], const uint32_t (&d1)[8], uint32_t (&a3)[2][4]) {
  const uint32_t ur = d0[2 * J], ui = d0[4 + 2 * J], hr = d0[2 * J + 1], hi = d0[5 + 2 * J];
  const uint32_t vr = d1[2 * J], vi = d1[4 + 2 * J], gr = d1[2 * J + 1], gi = d1[5 + 2 * J];
  const uint32_t pr = hfnma(ui, hi, hmul(ur, hr)), pi = hfma(ui, hr, hmul(ur, hi));
  a3[0][2 + C] = pr;
  a3[0][C] = pi;
  a3[1][2 + C] = hfnma(vi, hi, hfma(vr, hr, hfnma(ui, gi, hfms(ur, gr, pi))));
  a3[1][C] = hfma(vi, hr, hfma(vr, hi, hfma(ui, gr, hfma(ur, gi, pr))));
}
__device__ __forceinline__ void fft_e3(const uint32_t (&d)[2][8], const uint32_t (&tw)[16], uint32_t zaddr) {
#pragma unroll
  for (int rho = 0; rho < 2; rho++) {
    uint32_t zr[4], zi[4];
#pragma unroll
    for (int nb = 0; nb < 4; nb++) {
      const uint32_t xi = d[nb >> 1][2 * (nb & 1) + rho], xr = d[nb >> 1][4 + 2 * (nb & 1) + rho];
      const uint32_t tr = tw[8 + 4 * rho + 2 * (nb & 1)], ti = tw[9 + 4 * rho + 2 * (nb & 1)];
      zr[nb] = hfnma(xi, ti, hmul(xr, tr));
      zi[nb] = hfma(xi, tr, hmul(xr, ti));
    }
    stsm4(zaddr + rho * 2048, zr[0], zr[1], zr[2], zr[3]);
    stsm4(zaddr + rho * 2048 + 1024, zi[0], zi[1], zi[2], zi[3]);
  }
}
__device__ __forceinline__ float bf_lo(uint32_t v) {
  uint32_t r;
  asm("prmt.b32 %0, %1, 0, 0x1044;\n" : "=r"(r) : "r"(v));
  return __uint_as_float(r);
}
__device__ __forceinline__ float bf_hi(uint32_t v) { return __uint_as_float(v & 0xffff0000u); }
__device__ __forceinline__ float ex2(float x) {
  float r;
  asm("ex2.approx.ftz.f32 %0, %1;\n" : "=f"(r) : "f"(x));
  return r;
}
__device__ __forceinline__ float rcp(float x) {
  float r;
  asm("rcp.approx.ftz.f32 %0, %1;\n" : "=f"(r) : "f"(x));
  return r;
}

__device__ __forceinline__ int g2_a(int s) { return ((0xA1054 >> (4 * s)) & 15) * 16384; }
__device__ __forceinline__ int g2_b(int s) { return ((0xCDB32 >> (4 * s)) & 15) * 16384; }
static_assert(OFF_U == 10 * 16384 && OFF_H == 12 * 16384 && OFF_OP == 4 * 16384, "units");
__device__ __forceinline__ int g2_k(int hp, int i) {
  return i < 2 ? hp ^ 1 ^ i : i < 4 ? (hp & ~1) ^ i : ((hp & ~3) + i) & 15; }
__device__ __forceinline__ int y_slot(int wg, int it) {
  static_assert(T_B2 == T_TW + 8192 && T_A1 == T_B2 + 4096, "y slots");
  return OFF_T + T_TW + ((it + 3) & 3) * 4096 + wg * 2048;
}

__device__ __forceinline__ void to_arr(uint32_t (&d)[4], uint4 v) { d[0] = v.x; d[1] = v.y; d[2] = v.z; d[3] = v.w; }

__device__ __forceinline__ void attn_stage(uint32_t sb, int blk, int lane, const float (&acc)[96], uint32_t (&k1)[2][4]) {
  const int lr = lane & 7, lm = lane >> 3;
  const uint32_t base = sb + OFF_VP + (blk * 16 + lr + 8 * (lm & 1)) * 128;
#pragma unroll
  for (int i = 0; i < 8; i++) k1[i >> 2][i & 3] = pack_bf16(acc[34 + 4 * i], acc[35 + 4 * i]);
  const uint32_t kh = sb + OFF_KH + blk * 2048 + lane * 16;
  sts128(kh, k1[0][0], k1[0][1], k1[0][2], k1[0][3]);
  sts128(kh + 512, k1[1][0], k1[1][1], k1[1][2], k1[1][3]);
#pragma unroll
  for (int j = 0; j < 8; j += 2)
    stsm4(base + (((j + (lm >> 1)) ^ lr) << 4), pack_bf16(acc[64 + 4 * j], acc[65 + 4 * j]),
          pack_bf16(acc[66 + 4 * j], acc[67 + 4 * j]), pack_bf16(acc[68 + 4 * j], acc[69 + 4 * j]),
          pack_bf16(acc[70 + 4 * j], acc[71 + 4 * j]));
}
__device__ __forceinline__ void attn_pack(const float (&acc)[96], uint32_t (&qa)[2][8], uint32_t (&k0)[2][4]) {
#pragma unroll
  for (int hd = 0; hd < 2; hd++) {
#pragma unroll
    for (int i = 0; i < 8; i++) {
      asm volatile("cvt.rn.bf16x2.f32 %0, %1, %2;\n" : "=r"(qa[hd][i]) : "f"(acc[16 * hd + 2 * i + 1]), "f"(acc[16 * hd + 2 * i]));
    }
#pragma unroll
    for (int i = 0; i < 4; i++) {
      asm volatile("cvt.rn.bf16x2.f32 %0, %1, %2;\n" : "=r"(k0[hd][i]) : "f"(acc[33 + 16 * hd + 4 * i]), "f"(acc[32 + 16 * hd + 4 * i]));
    }
  }
}
__device__ __forceinline__ void attn_own(const uint32_t (&k0)[2][4], const uint32_t (&k1)[2][4], bool le0, bool le1,
                                         const uint32_t (&qa)[2][8], float (&l)[2][4]) {
#pragma unroll
  for (int hd = 0; hd < 2; hd++) {
    float s0[4], s1[4];
    mma16816_z(s0, qa[hd][0], qa[hd][1], qa[hd][2], qa[hd][3], k0[hd][0], k0[hd][1]);
    mma16816_z(s1, qa[hd][0], qa[hd][1], qa[hd][2], qa[hd][3], k1[hd][0], k1[hd][1]);
    mma16816(s0, qa[hd][4], qa[hd][5], qa[hd][6], qa[hd][7], k0[hd][2], k0[hd][3]);
    mma16816(s1, qa[hd][4], qa[hd][5], qa[hd][6], qa[hd][7], k1[hd][2], k1[hd][3]);
    l[hd][0] = s0[0];
    l[hd][1] = s0[1];
    l[hd][2] = le0 ? s1[2] : s0[2];
    l[hd][3] = le1 ? s1[3] : s0[3];
  }
}
template <int N> __device__ __forceinline__ void quad_softmax(float (&x)[N][2], uint32_t (&pp)[N]) {
  const float c2 = 1.4426950408889634f;
  uint32_t q[N], mx[N / 2];
#pragma unroll
  for (int n = 0; n < N; n++) {
    const uint32_t r = pack_bf16(x[n][0], x[n][1]);
    q[n] = bfma2(r, 0x3e353e35u, bmul2(r, 0x379e379eu));
    x[n][0] = bf_lo(q[n]);
    x[n][1] = bf_hi(q[n]);
  }
#pragma unroll
  for (int n = 0; n < N / 2; n++)
    mx[n] = bmax2(__byte_perm(q[2 * n], q[2 * n + 1], 0x5410), __byte_perm(q[2 * n], q[2 * n + 1], 0x7632));
#pragma unroll
  for (int o = 1; o <= 2; o++)
#pragma unroll
    for (int n = 0; n < N / 2; n++) mx[n] = bmax2(mx[n], __shfl_xor_sync(0xffffffffu, mx[n], o));
  float m[N], t[N];
#pragma unroll
  for (int n = 0; n < N / 2; n++) {
    m[2 * n] = bf_lo(mx[n]);
    m[2 * n + 1] = bf_hi(mx[n]);
  }
#pragma unroll
  for (int n = 0; n < N; n++) {
    const float nm = -m[n] * c2;
    x[n][0] = ex2(fmaf(x[n][0], c2, nm));
    x[n][1] = ex2(fmaf(x[n][1], c2, nm));
    t[n] = x[n][0] + x[n][1];
  }
#pragma unroll
  for (int o = 1; o <= 2; o++)
#pragma unroll
    for (int n = 0; n < N; n++) t[n] += __shfl_xor_sync(0xffffffffu, t[n], o);
#pragma unroll
  for (int n = 0; n < N; n++) {
    const float inv = rcp(t[n]);
    pp[n] = pack_bf16(x[n][0] * inv, x[n][1] * inv);
  }
}
__device__ __forceinline__ void attn_pv(uint32_t dst, const uint32_t (&va)[4], const uint32_t (&vb)[4], uint32_t pp,
                                        uint32_t maskLE) {
  const uint32_t b0 = pp & ~maskLE, b1 = pp & maskLE;
  float oa[4], ob[4];
  mma16816_z(oa, va[0], va[1], va[2], va[3], b0, b1);
  mma16816_z(ob, vb[0], vb[1], vb[2], vb[3], b0, b1);
  stsm4t(dst, pack_bf16(oa[0], oa[1]), pack_bf16(oa[2], oa[3]), pack_bf16(ob[0], ob[1]), pack_bf16(ob[2], ob[3]));
}

template <int MODE>
__global__ void __cluster_dims__(2, 1, 1) __launch_bounds__(NTHREADS, 1)
fused_kernel(const Params p, const __grid_constant__ CUtensorMap tmX, const __grid_constant__ CUtensorMap tmW,
             const __grid_constant__ CUtensorMap tmWo,
             const __grid_constant__ CUtensorMap tmQ,
             const __grid_constant__ CUtensorMap tmXh, const __grid_constant__ CUtensorMap tmWh) {
  extern __shared__ __align__(1024) uint8_t smem[];
  const uint32_t sb = smem_u32(smem) - OFF_L0;
  const uint32_t bars = sb + OFF_BAR;
  const int tid = threadIdx.x, lane = tid & 31, warp = __shfl_sync(0xffffffffu, tid >> 5, 0);
  const int rank = blockIdx.x & 1;
  const bool halo_cta = blockIdx.x < 4;
  if (halo_cta && MODE != 0) return;
  int grp, mem;
  {
    const int t = (blockIdx.x >> 1) - 4, u = t - 32;
    const int q7 = (u * 37) >> 8;
    const bool lo = (unsigned)t < 32u, mid = (unsigned)u < 28u;
    grp = lo ? (t & 7) : (mid ? 1 + u - 7 * q7 : 0);
    mem = lo ? (t >> 3) : (mid ? 4 + q7 : (t < 0 ? t + 6 : t - 54));
  }
  const int rg = (grp >> 2) * 4 + (mem >> 1), hp = (grp & 3) * 4 + (mem & 1) * 2 + rank;
  const int rb2 = (grp >> 2) * 8 + mem, cb2 = (grp & 3) * 2 + rank;
  const int chb = grp * 16 + mem * 2 + rank;
  const int cta = rg * 16 + hp;
  const int par = rg >> 2, gidx = rg & 3;

  if (tid < 256 && !halo_cta && MODE != 2) {
    const int r = tid >> 3, c = tid & 7;
    const uint32_t so = r * 128 + ((c ^ (r & 7)) << 4);
    const __nv_bfloat16* wg0 = p.w + (size_t)r * (3 * DM) + hp * 64 + c * 8;
    const __nv_bfloat16* xg0 = p.x + (size_t)(2 * (gidx * 256 + r) + par) * DM + c * 8;
#pragma unroll
    for (int j = 0; j < 3; j++) cp_async16n(sb + OFF_1B + j * 4096 + so, wg0 + j * DM);
#pragma unroll
    for (int i = 0; i < 8; i++) cp_async16n(sb + i * 4096 + so, xg0 + (size_t)i * 64 * DM);
    asm volatile("cp.async.commit_group;\n" ::: "memory");
  }
  if (tid == 256) {
    prefetch_tmap(halo_cta ? &tmXh : &tmX);
#pragma unroll
    for (int i = 0; i < NS1B; i++) mbar_init(bars + 8 * (BAR_FULLB + i), 1);
#pragma unroll
    for (int i = 0; i < NS1A; i++) mbar_init(bars + 8 * (BAR_FULLA + i), 1);
    asm volatile("fence.mbarrier_init.release.cluster;\n" ::: "memory");
    if (!halo_cta && MODE != 2) {
      mbar_expect_tx(bars + 8 * (BAR_FULLB + 1), STG1B);
      tma_load_3d(sb + OFF_1B + 1 * STG1B, &tmW, bars + 8 * (BAR_FULLB + 1), hp * 64, 32, 0);
      mbar_expect_tx(bars + 8 * (BAR_FULLB + 2), STG1B);
      tma_load_3d(sb + OFF_1B + 2 * STG1B, &tmW, bars + 8 * (BAR_FULLB + 2), hp * 64, 64, 0);
    } else {
      prefetch_tmap(&tmWh);
    }
  } else if (tid == 288) {
#pragma unroll
    for (int i = 0; i < NS1A; i++) mbar_init(bars + 8 * (BAR_EMPTYA + i), 4);
#pragma unroll
    for (int i = 0; i < NS1B; i++) mbar_init(bars + 8 * (BAR_EMPTYB + i), 2);
    asm volatile("fence.mbarrier_init.release.cluster;\n" ::: "memory");
  } else if (tid == 320) {
#pragma unroll
    for (int i = 0; i < NS2; i++) {
      mbar_init(bars + 8 * (BAR_FULL2 + i), 1);
      mbar_init(bars + 8 * (BAR_EMPTY2 + i), 4);
    }
    mbar_init(bars + 8 * BAR_DEAD, 2);
    mbar_init(bars + 8 * (BAR_DEAD + 1), 2);
    mbar_init(bars + 8 * BAR_X, 2);
    mbar_init(bars + 8 * BAR_REL, 2);
    asm volatile("fence.mbarrier_init.release.cluster;\n" ::: "memory");
  } else if (tid == 352) {
    mbar_init(bars + 8 * BAR_T, 1);
    mbar_init(bars + 8 * BAR_UH, 3);
    mbar_init(bars + 8 * BAR_LFREE, 4);
    mbar_init(bars + 8 * BAR_LAND, 1);
    mbar_init(bars + 8 * BAR_U, 1);
    mbar_init(bars + 8 * BAR_Q, 1);
    mbar_init(bars + 8 * BAR_STG, 9);
    asm volatile("fence.mbarrier_init.release.cluster;\n" ::: "memory");
  }
  if (warp == 8) PROF2(23);
  cluster_sync_all();
  if (warp == 8) PROF2(24);

  if (warp >= 8) {
    const int hw = warp - 8;
    const int lr = lane & 7, lm = lane >> 3;
    auto g1_issue_a = [&](int j, int s) {
      const uint32_t fb = bars + 8 * (BAR_FULLA + s);
      mbar_expect_tx(fb, STG1A);
      tma_load_3d_mc(sb + s * STG1A + rank * 16384, &tmX, fb, j * 64, par, gidx * 256 + rank * 128);
    };
    auto g1_issue_b = [&](int kb, int s) {
      const uint32_t fb = bars + 8 * (BAR_FULLB + s);
      mbar_expect_tx(fb, STG1B);
      tma_load_3d(sb + OFF_1B + s * STG1B, &tmW, fb, hp * 64, kb * 32, 0);
    };
    asm volatile("setmaxnreg.dec.sync.aligned.u32 %0;\n" :: "n"(REG_HELP));

    if (halo_cta) {
      if (hw == 0) {
        int s = 0, ph = 1;
#pragma unroll 1
        for (int kb = 0; kb < 16; kb++) {
          mbar_wait(bars + 8 * (BAR_EMPTYB + s), ph);
          const uint32_t fb = bars + 8 * (BAR_FULLB + s), st = sb + s * STGH;
          if (elect_one()) {
            mbar_expect_tx(fb, STGH);
            tma_load_4d(st, &tmXh, fb, kb * 64, 248, 0, 0);
            tma_load_3d(st + 8192, &tmWh, fb, 0, kb * 64, 16 + blockIdx.x * 4);
            tma_load_3d(st + 8192 + 32768, &tmWh, fb, 0, kb * 64, 32 + blockIdx.x * 4);
          }
          if (++s == 3) { s = 0; ph ^= 1; }
        }
      }
      __syncwarp();
    } else if (hw == 0) {
      uint32_t epoch = 0;
      if (lane < (MODE == 2 ? NS2 : 2)) mbar_arrive_cluster_n(mapa(bars, rank) + 8 * (BAR_EMPTY2 + lane), 4);
      if (MODE != 2) {
      epoch = ld_relaxed(g_flag_o + 2 * cta) + 1;
      if (lane == 0) {
        mbar_expect_tx(bars + 8 * BAR_U, 32768);
        mbar_expect_tx(bars + 8 * BAR_LAND, 32768 + 64);
        mbar_expect_tx(bars + 8 * BAR_Q, 32768);
        mbar_expect_tx(bars + 8 * BAR_T, T_END);
      }
      {
        int sa = 1, pha = 1, sbb = 2, phb = 1;
#pragma unroll 1
        for (int kb = 2; kb < 32; kb++) {
          if (!(kb & 1)) {
            mbar_wait(bars + 8 * (BAR_EMPTYA + sa), pha);
            if (elect_one()) g1_issue_a(kb >> 1, sa);
            if (++sa == NS1A) { sa = 0; pha ^= 1; }
          }
          mbar_wait(bars + 8 * (BAR_EMPTYB + sbb), phb);
          if (kb > 2 && elect_one()) g1_issue_b(kb, sbb);
          __syncwarp();
          if (kb >= PF0 && kb < PF0 + 12)
            prefetch_l2((kb < PF0 + 8 ? p.q + (size_t)chb * 16384 + (kb - PF0) * 2048 : p.wo + (size_t)chb * 8192 + (kb - PF0 - 8) * 2048) + lane * 64);
          if (kb == 4) PROF2(27);
          if (kb == 1) PROF2(38);
          if (kb == 2) PROF2(39);
          if (++sbb == NS1B) { sbb = 0; phb ^= 1; }
        }
      }
      static_assert(32 % NS1B == 2 && (32 / NS1B) % 2 == 0 && OFF_Q == OFF_1B && 2 * STG1B == 6 * 4096, "slots / parity of these loads");
      const uint8_t* tab = reinterpret_cast<const uint8_t*>(g_tab);
      if (lane == 0) {
        prefetch_tmap(&tmWo);
        prefetch_tmap(&tmQ);
        bulk_load(sb + OFF_T + T_A1, tab + T_A1, T_END - T_A1, bars + 8 * BAR_T);
        mbar_wait(bars + 8 * (BAR_EMPTYB + 2), 1);
        tma_load_5d(sb + OFF_Q + 6 * 4096, &tmQ, bars + 8 * BAR_Q, (chb & ~1) * 8, rank * 32 + 24);
        tma_load_5d(sb + OFF_Q + 7 * 4096, &tmQ, bars + 8 * BAR_Q, (chb & ~1) * 8, rank * 32 + 28);
        if (gidx != 0) wait_flag(g_flag_h + (hp >> 2), epoch);
      }
      __syncwarp();
      {
        uint4 hk0 = make_uint4(0, 0, 0, 0), hk1 = hk0, hv0 = hk0, hv1 = hk0;
        if (gidx != 0) {
          const uint4* src = g_halo + cta * 128 + lane;
          hk0 = __ldcg(src); hk1 = __ldcg(src + 32); hv0 = __ldcg(src + 64); hv1 = __ldcg(src + 96);
        }
        if (lane == 0) {
          mbar_wait(bars + 8 * (BAR_EMPTYB + 3), 1);
          bulk_load(sb + OFF_T, tab, T_TW, bars + 8 * BAR_T);
        }
        __syncwarp();
        PROF2(18);
        sts128(sb + OFF_L0 + lane * 16, hk0.x, hk0.y, hk0.z, hk0.w);
        sts128(sb + OFF_L0 + 512 + lane * 16, hk1.x, hk1.y, hk1.z, hk1.w);
        stsm4(sb + OFF_L0 + 1024 + lr * 128 + ((lm ^ lr) << 4), hv0.x, hv0.y, hv0.z, hv0.w);
        stsm4(sb + OFF_L0 + 1024 + lr * 128 + (((4 + lm) ^ lr) << 4), hv1.x, hv1.y, hv1.z, hv1.w);
        __syncwarp();
        if (lane == 0) {
          mbar_arrive(bars + 8 * BAR_STG);
          mbar_wait(bars + 8 * (BAR_EMPTYB + 4), 1);
          bulk_load(sb + OFF_T + T_TW, tab + T_TW, T_A1 - T_TW, bars + 8 * BAR_T);
          mbar_wait(bars + 8 * BAR_EMPTYB, 0);
#pragma unroll 1
          for (int i = 0; i < 6; i++) tma_load_5d(sb + OFF_Q + i * 4096, &tmQ, bars + 8 * BAR_Q, (chb & ~1) * 8, rank * 32 + i * 4);
        }
        __syncwarp();
      }
      }
      if (MODE != 1) {
        auto korder = [&](int i) { return MODE == 2 ? i : g2_k(hp, i); };
        const __nv_bfloat16* osrc = g_o + (size_t)(rb2 >> 1) * 16 * 16384 + ((rb2 & 1) * 2 + rank) * 4096;
        const uint32_t* flag = g_flag_o + ((rb2 >> 1) * 32 + korder(lane & 15) * 2 + (rb2 & 1));
        uint32_t ready = MODE == 0 ? 0u : ~0u, pv = 0;
        auto look = [&]() {
          ready |= __ballot_sync(0xffffffffu, pv == epoch);
          asm volatile("fence.acquire.gpu;\n" ::: "memory");
          fence_async_all();
        };
        const __nv_bfloat16* o23[2] = {osrc + korder(2) * 16384, osrc + korder(3) * 16384};
        if (MODE == 0) {
          asm volatile("" : "+l"(o23[0]), "+l"(o23[1]), "+l"(flag));
          if (lane < 4 && lane != 1) mbar_expect_tx(bars + 8 * (BAR_FULL2 + lane), STG2);
          mbar_wait_idle(bars + 8 * (BAR_EMPTY2 + 2), 0);
          mbar_wait(bars + 8 * (BAR_EMPTY2 + 3), 0);
          mbar_wait_idle(bars + 8 * BAR_REL, 0);
          if (elect_one()) {
            tma_load_3d(sb + g2_b(0), &tmWo, bars + 8 * BAR_FULL2, 0, korder(0) * 64, cb2 * 2);
            tma_load_3d(sb + g2_b(1), &tmWo, bars + 8 * (BAR_FULL2 + 1), 0, korder(1) * 64, cb2 * 2);
          }
        }
#pragma unroll
        for (int i = MODE == 0 ? 2 : 0; i < 16; i++) {
          const int kb = korder(i), s = i % NS2, ph = (i / NS2) & 1;
          const uint32_t fb = bars + 8 * (BAR_FULL2 + s);
          if (!((ready >> i) & 1)) {
            int n = 0;
            do {
              ready |= __ballot_sync(0xffffffffu, ld_acquire(flag) == epoch);
            } while (!((ready >> i) & 1) && ++n < SPIN_LIMIT);
            fence_async_all();
          }
          if (i == 2) PROF(21);
          const bool pre = MODE == 0 && i < 4;
          if (!pre) mbar_wait(bars + 8 * (BAR_EMPTY2 + s), ph);
          if (elect_one()) {
            if (!pre) mbar_expect_tx(fb, STG2);
            asm volatile(
                "cp.async.bulk.shared::cluster.global.mbarrier::complete_tx::bytes.multicast::cluster [%0], [%1], %2, [%3], %4;\n"
                ::"r"(sb + g2_a(s) + rank * 8192), "l"(pre ? o23[i & 1] : osrc + kb * 16384), "r"(8192), "r"(fb), "h"((uint16_t)3) : "memory");
            if (!pre) tma_load_3d(sb + g2_b(s), &tmWo, fb, 0, kb * 64, cb2 * 2);
          }
          if (MODE == 0 && i == LA0) pv = ld_relaxed(flag);
          if (MODE == 0 && i == LA1) look();
          if (i == 3) PROF(37);

        }
      }
      __syncwarp();
    } else if (MODE != 2) {
      {
        const int g = lane >> 2, t = lane & 3;
        uint32_t w[2][4];
#pragma unroll
        for (int h = 0; h < 2; h++) {
          const uint2 x = __ldg(reinterpret_cast<const uint2*>(p.shift_k + ((chb & ~1) * 8 + h * 8 + g) * 4));
          w[h][0] = __byte_perm(x.x, x.x, 0x1010);
          w[h][1] = __byte_perm(x.x, x.x, 0x3232);
          w[h][2] = __byte_perm(x.y, x.y, 0x1010);
          w[h][3] = __byte_perm(x.y, x.y, 0x3232);
        }
        auto swz = [](int r) { return (((r & 29) | ((r ^ (r >> 2)) & 2)) << 5) | (r & 16); };
        const uint32_t kring = sb + OFF_H + (hw - 1) * 8192, vring = kring + 4096;
        const int s0 = rank * 32 + (hw - 1) * 11, s1 = hw == 3 ? rank * 32 + 32 : s0 + 11;
        const size_t goff = (size_t)(lane >> 1) * DM + (chb & ~1) * 8 + (lane & 1) * 8;
        const __nv_bfloat16* kg = p.k + goff;
        const __nv_bfloat16* vg = p.v + goff;
        const uint32_t d0 = swz(lane >> 1) ^ ((lane & 1) << 4), d1 = swz(16 + (lane >> 1)) ^ ((lane & 1) << 4);
        auto issue = [&](int st) {
          const uint32_t so = (st & 3) << 10;
          cp_async16(kring + so + d0, kg + (size_t)st * 32 * DM, 16);
          cp_async16(kring + so + d1, kg + (size_t)(st * 32 + 16) * DM, 16);
          cp_async16(vring + so + d0, vg + (size_t)st * 32 * DM, 16);
          cp_async16(vring + so + d1, vg + (size_t)(st * 32 + 16) * DM, 16);
        };
        const int xa = 8 * (lr >> 1) + 2 * lm + (lr & 1), xb = 8 * (lr >> 1) - 4 + 2 * (lm & 1) + (lr & 1);
        const uint32_t la = swz(xa), lb = swz(xb & 31);
        const int backb = xb < 0 ? 1 : 0;
        const uint32_t ud[2] = {mapa(sb + OFF_U + g * 4096 + t * 16, 0), mapa(sb + OFF_U + g * 4096 + t * 16, 1)};
        const uint32_t ub[2] = {mapa(bars + 8 * BAR_U, 0), mapa(bars + 8 * BAR_U, 1)};
        if (lane == 0) mbar_wait(bars + 8 * (BAR_FULLB + NS1B - 1), 0);
        __syncwarp();
        if (lane >= 24) cp_async16(kring + (((s0 - 1) & 3) << 10) + d1, s0 > 0 ? kg + (size_t)(s0 * 32 - 16) * DM : kg, s0 > 0 ? 16 : 0);
        issue(s0);
        asm volatile("cp.async.commit_group;\n" ::: "memory");
        issue(s0 + 1);
        asm volatile("cp.async.commit_group;\n" ::: "memory");
#pragma unroll 1
        for (int st = s0; st < s1; st++) {
          if (st + 2 < s1) issue(st + 2);
          if (hw == 1 && st - s0 < 8) prefetch_l2(p.ssm_k + (size_t)(chb * 8 + st - s0) * SEQ + lane * 64);
          if (hw == 2 && st == s0 + 4 && lane < 2) prefetch_l2(g_tab + (chb * 2 + lane) * 32);
          const uint32_t uo = (st ^ ((g ^ (st >> 2)) & 1)) * 64;
          asm volatile("cp.async.commit_group;\n" ::: "memory");
          asm volatile("cp.async.wait_group 2;\n" ::: "memory");
          __syncwarp();
#pragma unroll
          for (int h = 0; h < 2; h++) {
            uint32_t e[6], vv[4], e4[4];
            ldsm4t(e4, kring + ((st & 3) << 10) + (la ^ (h << 4)));
            ldsm2t(e[0], e[1], kring + (((st - backb) & 3) << 10) + (lb ^ (h << 4)));
            ldsm4t(vv, vring + ((st & 3) << 10) + (la ^ (h << 4)));
            e[2] = e4[0]; e[3] = e4[1]; e[4] = e4[2]; e[5] = e4[3];
            uint32_t o[5];
#pragma unroll
            for (int i = 0; i < 5; i++) o[i] = __byte_perm(e[i], e[i + 1], 0x5432);
#pragma unroll
            for (int i = 0; i < 4; i++) {
              uint32_t a = bmul2(o[i], w[h][3]);
              a = bfma2(e[i + 1], w[h][2], a);
              a = bfma2(o[i + 1], w[h][1], a);
              a = bfma2(e[i + 2], w[h][0], a);
              vv[i] = bmul2(a, vv[i]);
            }
            st_async128(ud[h] + uo, ub[h], vv[0], vv[1], vv[2], vv[3]);
          }
          __syncwarp();
        }
        PROF(16);
      }
      {
        const int rw = (lane >> 3) + (lane & 4), ck = lane & 3;
        const uint32_t so = rw * 64 + ck * 16, dof = rw * 128 + ((ck ^ rw) << 4);
        const uint8_t* hsrc = reinterpret_cast<const uint8_t*>(p.ssm_k + (size_t)chb * 8 * SEQ) + so;
        const float dv = lane < 8 ? __bfloat162float(p.ssm_D[chb * 8 + lane]) : 0.f;
        uint32_t x[32];
        auto load = [&](const uint8_t* src, int i) {
          asm volatile("ld.v4.u32 {%0,%1,%2,%3}, [%4];\n" : "=r"(x[4 * i]), "=r"(x[4 * i + 1]), "=r"(x[4 * i + 2]), "=r"(x[4 * i + 3])
                       : "l"(src + i * 512) : "memory");
        };
#pragma unroll
        for (int i = 0; i < 8; i++) load(hsrc + (hw - 1) * 4096, i);
        nb_sync(NB_HELP3, 96);
        mbar_wait(bars + 8 * BAR_U, 0);
        int eh = 0;
#pragma unroll 1
        for (int n = 2 * (hw - 1); n < 16; n += (n & 1) ? 5 : 1) {
          const int c = n >> 1;
          const uint8_t* nsrc = (n & 1) ? hsrc + (c < 5 ? c + 3 : c) * 4096
                                        : smem - OFF_L0 + OFF_U + c * 4096 + (so ^ (((c ^ (lane >> 2)) & 1) << 6));
          const uint32_t dst = sb + ((n & 1) ? OFF_U : OFF_H) + c * 4096 + dof;
          const float dc = __shfl_sync(0xffffffffu, dv, c);
          const float h0 = bf_lo(x[0]) + ((lane | (n & 1)) == 0 ? dc : 0.f), h1 = bf_hi(x[0]);
          x[0] = pack_bf16(h0, h1);
          uint32_t m[2] = {x[0], x[1]};
#pragma unroll
          for (int i = 2; i < 32; i++) asm("max.xorsign.abs.bf16x2 %0, %0, %1;\n" : "+r"(m[i & 1]) : "r"(x[i]));
          asm("max.xorsign.abs.bf16x2 %0, %0, %1;\n" : "+r"(m[0]) : "r"(m[1]));
          const uint32_t e = max(__reduce_max_sync(0xffffffffu, max((m[0] >> 7) & 255u, (m[0] >> 23) & 255u)), 5u);
          const uint32_t sc = (259u - e) * 0x00800080u;
#pragma unroll
          for (int i = 0; i < 8; i++) {
            uint32_t o[4];
#pragma unroll
            for (int j = 0; j < 4; j++) {
              const uint32_t v = bmul2(x[4 * i + j], sc);
              asm("cvt.rn.f16x2.f32 %0, %1, %2;\n" : "=r"(o[j]) : "f"(bf_hi(v)), "f"(i + j == 0 ? h0 * bf_hi(sc) : bf_lo(v)));
            }
            sts128((dst + (i & 3) * 1024) ^ ((i >> 2) << 6), o[0], o[1], o[2], o[3]);
            load(nsrc, i);
          }
          if (n & 1) {
            const int f = min(max((int)e + eh - 129, 0), 254);
            if (lane < 2)
              asm volatile("st.async.weak.shared::cluster.mbarrier::complete_tx::bytes.b32 [%0], %2, [%1];\n"
                           ::"r"(mapa(sb + OFF_SC + rank * 32 + c * 4, lane)), "r"(mapa(bars + 8 * BAR_LAND, lane)), "r"(f << 7) : "memory");
          }
          eh = e;
        }
        fence_async_smem();
        __syncwarp();
        if (lane == 0) mbar_arrive(bars + 8 * BAR_UH);
        PROF(32);
      }
      if (hw < 3) {
        const uint32_t rb = mapa(bars, lane & 1);
        const uint32_t epoch = ld_relaxed(g_flag_o + (2 * cta + hw - 1)) + 1;
        const bool own = hw - 1 == (rb2 & 1);
        nb_sync(NB_OREADY + hw - 1, 160);
        if (lane == 0) {
          asm volatile("cp.async.bulk.global.shared::cta.bulk_group [%0], [%1], %2;\n" ::"l"(g_o + (size_t)cta * 16384 + (hw - 1) * 8192),
                       "r"(sb + OFF_OP + (own ? 16384 : 0)), "r"(16384) : "memory");
          bulk_commit();
        }
        if (lane < 2) {
          mbar_arrive_cluster(rb + 8 * (BAR_EMPTY2 + 2));
          mbar_arrive_cluster(rb + 8 * (BAR_EMPTY2 + 3));
        }
        if (lane == 0) {
          bulk_wait0();
          if (own) mbar_expect_tx(bars + 8 * (BAR_FULL2 + 1), 16384);
          mbar_arrive_cluster(mapa(bars, own ? rank : rank ^ 1) + 8 * BAR_X);
          st_release(g_flag_o + (2 * cta + hw - 1), epoch);
          mbar_arrive(bars + 8 * BAR_REL);
        }
        __syncwarp();
        PROF(own ? 17 : 19);
      } else {
        if (MODE == 0) {
          mbar_wait_idle(bars + 8 * BAR_X, 0);
          if (elect_one())
            asm volatile("cp.async.bulk.shared::cluster.shared::cta.mbarrier::complete_tx::bytes [%0], [%1], %2, [%3];\n"
                         ::"r"(mapa(sb + OFF_OP, rank ^ 1)), "r"(sb + OFF_OP + 16384), "r"(16384),
                         "r"(mapa(bars + 8 * BAR_FULL2, rank ^ 1)) : "memory");
        }
        if (MODE == 0) {
          mbar_wait_idle(bars + 8 * BAR_DEAD, 0);
          if (elect_one()) {
            tma_load_3d(sb + g2_b(2), &tmWo, bars + 8 * (BAR_FULL2 + 2), 0, g2_k(hp, 2) * 64, cb2 * 2);
            tma_load_3d(sb + g2_b(3), &tmWo, bars + 8 * (BAR_FULL2 + 3), 0, g2_k(hp, 3) * 64, cb2 * 2);
          }
        }
        __syncwarp();
      }
    }
    if (!halo_cta && MODE != 2 && (F4 || hw)) {
      {
        const int c8 = (4 * (lr >> 1) + 2 * (lm & 1) + (lr & 1)) & 7;
        const bool own = (lr >> 2) == rank;
        const uint32_t ya = sb + (own ? y_slot(c8 & 1, c8 >> 1) : OFF_LAND + c8 * 2048);
        const uint32_t yx = ((lm >> 1) ^ lr) << 4;
        const int row = (lane >> 4) * 8 + ((lane >> 3) & 1) * 16 + ((lane >> 2) & 1);
        uint2* og = reinterpret_cast<uint2*>(p.out + (size_t)(rank * 1024 + row) * (2 * DM) + (chb & ~1) * 8 + (lane & 3) * 4);
        const uint32_t qa = sb + OFF_Q + (lane >> 4) * 512 + (lane & 15) * 8;
        mbar_wait(bars + 8 * BAR_Q, 0);
        mbar_wait_idle(bars + 8 * BAR_LAND, 0);
        PROF(33);
        const uint32_t t0 = clock();
        const uint4 s4 = lds128(sb + OFF_SC + (lane & 3) * 16);
        const uint32_t sc[2] = {s4.x | (s4.y << 16), s4.z | (s4.w << 16)};
        auto fin = [&](uint32_t q2, uint32_t y2, uint32_t s2) {
          float lo, hi;
          asm("{\n.reg .b16 l, h;\nmov.b32 {l, h}, %2;\ncvt.f32.f16 %0, l;\ncvt.f32.f16 %1, h;\n}\n" : "=f"(lo), "=f"(hi) : "r"(y2));
          return bmul2(q2, bmul2(pack_bf16(lo, hi), s2));
        };
#pragma unroll 1
        for (int j = hw ? hw - 1 : 15; j < (hw ? 16 - F4 : 16); j += 3) {
          uint32_t y[4][4];
          uint2 q[8];
          while (hw && (uint32_t)clock() - t0 < j * PACE) __nanosleep(40);
          const uint32_t qj = qa + j * 2048;
#pragma unroll
          for (int i = 0; i < 4; i++) ldsm4t(y[i], ya + j * 128 + (yx ^ (i << 5)));
#pragma unroll
          for (int i = 0; i < 8; i++) q[i] = lds64(qj + (i >> 2) * 1024 + (i & 3) * 128);
#pragma unroll
          for (int i = 0; i < 8; i++) {
            og[(size_t)(j * 64 + (i >> 2) * 32 + (i & 3) * 2) * (2 * DM / 4)] =
                make_uint2(fin(q[i].x, y[i >> 1][2 * (i & 1)], sc[0]), fin(q[i].y, y[i >> 1][2 * (i & 1) + 1], sc[1]));
            if (i < 7) asm volatile("nanosleep.u32 %0;\n" ::"r"(FINE) : "memory");
          }
        }
      }
      PROF(22);
    }
    cluster_sync_all();
  } else {
    asm volatile("setmaxnreg.inc.sync.aligned.u32 %0;\n" :: "n"(REG_MATH));
    if (warp == 0) PROF2(26);
    const int wg = warp >> 2;
    const int wtid = tid & 127;
    const bool signaller = (wtid == 0) || (wtid == 32);
    const uint32_t rbars = mapa(bars, wtid >> 5 & 1);

    if (halo_cta) {
      const uint32_t epoch = ld_relaxed(g_flag_h + blockIdx.x) + 1;
      float acc0[64], acc1[64];
      int s = 0, ph = 0;
#pragma unroll 1
      for (int kb = 0; kb < 16; kb++) {
        mbar_wait(bars + 8 * (BAR_FULLB + s), ph);
        const uint32_t st = sb + s * STGH;
        const uint64_t da = mkdesc(st, 16, 1024, 1);
        const uint64_t db = mkdesc(st + 8192 + wg * 32768, 8192, 1024, 1);
        wg_fence();
#pragma unroll
        for (int kk = 0; kk < 4; kk++) {
          wgmma_n128(acc0, da + 2 * kk, db + 128 * kk, kb + kk);
          wgmma_n128(acc1, da + 2 * kk, db + 1024 + 128 * kk, kb + kk);
        }
        wg_commit();
        wg_wait<0>();
        if (wtid == 0) mbar_arrive(bars + 8 * (BAR_EMPTYB + s));
        if (++s == 3) { s = 0; ph ^= 1; }
      }
      fence_regs(acc0);
      fence_regs(acc1);
      if ((warp & 3) != 3) {
#pragma unroll
        for (int hh = 0; hh < 2; hh++) {
          uint4* dst = g_halo + ((hh * 4 + (warp & 3) + 1) * 16 + blockIdx.x * 4) * 128 + wg * 64 + lane;
#pragma unroll
          for (int j = 0; j < 4; j++) {
            const int o = 16 * j + 2 * hh;
            dst[(j >> 1) * 128 + (j & 1) * 32] =
                make_uint4(pack_bf16(acc0[o], acc0[o + 1]), pack_bf16(acc0[o + 4], acc0[o + 5]),
                           pack_bf16(acc0[o + 8], acc0[o + 9]), pack_bf16(acc0[o + 12], acc0[o + 13]));
            dst[(2 + (j >> 1)) * 128 + (j & 1) * 32] =
                make_uint4(pack_bf16(acc1[o], acc1[o + 1]), pack_bf16(acc1[o + 4], acc1[o + 5]),
                           pack_bf16(acc1[o + 8], acc1[o + 9]), pack_bf16(acc1[o + 12], acc1[o + 13]));
          }
        }
      }
      nb_sync(NB_G1DONE, 256);
      if (tid == 0) st_release(g_flag_h + blockIdx.x, epoch);
      PROF(36);
      cluster_sync_all();
      return;
    }

    float acc[64];
    auto g2_step = [&](int s, int kb) {
      const uint64_t da = mkdesc(sb + g2_a(s) + wg * 8192, 16, 1024, 1);
      const uint64_t db = mkdesc(sb + g2_b(s), 8192, 1024, 1);
      wg_fence();
      wgmma_n128(acc, da, db, kb);
      wgmma_n128(acc, da + 2, db + 128, 1);
      wgmma_n128(acc, da + 4, db + 256, 1);
      wgmma_n128(acc, da + 6, db + 384, 1);
      wg_commit();
    };

    if (MODE != 2) {
    uint32_t a1[2][4], tw[16], d1[32];
    const uint32_t tb = sb + OFF_T + wtid * 16;
    const uint64_t dx = mkdesc(sb + OFF_U + wg * 4096, OFF_H - OFF_U, 1024, 1);
    auto s1 = [&](int it) {
      hmma_n128t<0>(d1, a1[0], dx + it * 512);
      hmma_n128t<1>(d1, a1[1], dx + it * 512 + 128);
      wg_commit();
    };
    auto ldtw = [&](int i) {
      const uint4 v = lds128(tb + T_TW + i * 2048);
      tw[4 * i] = v.x; tw[4 * i + 1] = v.y; tw[4 * i + 2] = v.z; tw[4 * i + 3] = v.w;
    };
    {
      float acc0[96], acc1[96];
      int sa = 0, pha = 0, sbb = 0, phb = 0;
      asm volatile("cp.async.wait_group 0;\n" ::: "memory");
      fence_async_smem();
      nb_sync(NB_FIRST, 256);
      if (tid == 0) {
        mbar_arrive(bars + 8 * BAR_FULLA);
        mbar_arrive(bars + 8 * BAR_FULLB);
      }
      PROF(0 + wg);
#pragma unroll 1
      for (int kb = 0; kb < 30; kb++) {
        if (!(kb & 1)) mbar_wait(bars + 8 * (BAR_FULLA + sa), pha);
        mbar_wait(bars + 8 * (BAR_FULLB + sbb), phb);
        if (kb == 0) PROF2(0 + wg);
        if (kb == 4 && wg == 0) PROF2(28);
        if (kb == 8 && wg == 0) PROF2(29);
        if (kb == 16 && wg == 0) PROF2(30);
        const uint64_t da = mkdesc(sb + sa * STG1A + wg * 16384 + (kb & 1) * 64, 16, 1024, 1);
        const uint64_t db = mkdesc(sb + OFF_1B + sbb * STG1B, 4096, 1024, 1);
        wg_fence();
        wgmma_n192(acc0, da, db, kb);
        wgmma_n192(acc1, da + 512, db, kb);
        wgmma_n192(acc0, da + 2, db + 128, 1);
        wgmma_n192(acc1, da + 514, db + 128, 1);
        wg_commit();
        wg_wait<1>();
        if (kb > 0) {
          if (wtid == 64) mbar_arrive(bars + 8 * (BAR_EMPTYB + (sbb == 0 ? NS1B - 1 : sbb - 1)));
          if (!(kb & 1) && signaller) mbar_arrive_cluster(rbars + 8 * (BAR_EMPTYA + (sa == 0 ? NS1A - 1 : sa - 1)));
        }
        if (++sbb == NS1B) { sbb = 0; phb ^= 1; }
        if ((kb & 1) && ++sa == NS1A) { sa = 0; pha ^= 1; }
      }
      const int blk0 = wg * 8 + (warp & 3);
      const int lr = lane & 7, lm = lane >> 3;
      const bool le0 = 2 * (lane & 3) <= (lane >> 2), le1 = 2 * (lane & 3) + 1 <= (lane >> 2);
      const uint32_t maskLE = (le0 ? 0x0000FFFFu : 0u) | (le1 ? 0xFFFF0000u : 0u);
      uint32_t k0[2][2][4], k1[2][2][4], qa[2][2][8];
      float l[2][2][4];
      {
        static_assert(15 % NS1A == 0 && 30 % NS1B == 0, "slots of the last k blocks");
        mbar_wait(bars + 8 * BAR_FULLA, 1);
        mbar_wait(bars + 8 * BAR_FULLB, 0);
        mbar_wait(bars + 8 * (BAR_FULLB + 1), 0);
        const uint64_t da = mkdesc(sb + wg * 16384, 16, 1024, 1);
        const uint64_t db = mkdesc(sb + OFF_1B, 4096, 1024, 1);
        wg_fence();
#pragma unroll
        for (int i = 0; i < 4; i++) wgmma_n192(acc0, da + 2 * i, db + (i >> 1) * (STG1B >> 4) + (i & 1) * 128, 1);
        wg_commit();
        wg_wait<1>();
        if (wtid == 64) mbar_arrive(bars + 8 * (BAR_EMPTYB + NS1B - 1));
#pragma unroll
        for (int i = 0; i < 2; i++) wgmma_n192(acc1, da + 512 + 2 * i, db + (i >> 1) * (STG1B >> 4) + (i & 1) * 128, 1);
        wg_commit();
        wg_wait<1>();
        fence_regs(acc0);
        attn_stage(sb, blk0, lane, acc0, k1[0]);
#pragma unroll
        for (int i = 2; i < 4; i++) wgmma_n192(acc1, da + 512 + 2 * i, db + (i >> 1) * (STG1B >> 4) + (i & 1) * 128, 1);
        wg_commit();
        attn_pack(acc0, qa[0], k0[0]);
        wg_wait<0>();
        fence_regs(acc1);
      }
      if (wtid == 64) mbar_arrive(bars + 8 * BAR_EMPTYB);
      PROF(2 + wg);
      attn_stage(sb, blk0 + 4, lane, acc1, k1[1]);
      __syncwarp();
      if (lane == 0) mbar_arrive(bars + 8 * BAR_STG);
      mbar_wait(bars + 8 * BAR_U, 0);
      attn_pack(acc1, qa[1], k0[1]);
      attn_own(k0[0], k1[0], le0, le1, qa[0], l[0]);
      attn_own(k0[1], k1[1], le0, le1, qa[1], l[1]);
      static_assert(OFF_L0 + 2048 == OFF_VP, "halo V rows");
      const uint32_t vl0 = sb + OFF_VP - 1024 + blk0 * 2048 + (lm >> 1) * 1024 + lr * 128 + (((lm & 1) ^ lr) << 4);
      const uint32_t vl[4] = {vl0, vl0 ^ 64, vl0 ^ 32, vl0 ^ 96};
      const uint32_t obase = sb + OFF_OP + (wg == (rb2 & 1) ? 16384 : 0) + ((warp & 3) * 16 + lr) * 128 + ((lm ^ lr) << 4);
      mbar_wait(bars + 8 * BAR_STG, 0);
      {
        uint32_t km[4][4], va[8][4], vb[8][4], pp[8];
        float x[8][2];
#pragma unroll
        for (int n = 0; n < 4; n++) {
          const int blk = blk0 + 4 * (n >> 1);
          to_arr(km[n], lds128(sb + (blk == 0 ? OFF_L0 : OFF_KH + (blk - 1) * 2048) + (n & 1) * 512 + lane * 16));
        }
#pragma unroll
        for (int n = 0; n < 8; n++) {
          const uint32_t o = ((n >> 1) & 1) * 8192 + (n >> 2) * 1024;
          ldsm4t(va[n], vl[n & 1] + o);
          ldsm4t(vb[n], vl[2 + (n & 1)] + o);
        }
        const bool first = blk0 == 0 && gidx == 0;
#pragma unroll
        for (int n = 0; n < 4; n++) {
          const uint32_t(&q)[8] = qa[n >> 1][n & 1];
          float sm[4];
          mma16816_z(sm, q[0], q[1], q[2], q[3], km[n][0], km[n][1]);
          mma16816(sm, q[4], q[5], q[6], q[7], km[n][2], km[n][3]);
          if (n < 2 && first) sm[0] = sm[1] = -1e9f / 0.17677669529663687f;
          x[n][0] = le0 ? l[n >> 1][n & 1][0] : sm[0];
          x[n][1] = le1 ? l[n >> 1][n & 1][1] : sm[1];
          x[4 + n][0] = l[n >> 1][n & 1][2];
          x[4 + n][1] = l[n >> 1][n & 1][3];
        }
        quad_softmax<8>(x, pp);
#pragma unroll
        for (int n = 7; n >= 0; n--)
          attn_pv((obase ^ ((n & 1) << 6)) + ((n >> 1) & 1) * 8192 + (n >> 2) * 1024, va[n], vb[n], pp[n], maskLE);
      }
      fence_async_smem();
      nb_arrive(NB_OREADY + wg, 160);
    }

    {
      const int w = warp & 3;
      uint32_t a4[8][4];
      uint32_t d4[16];
      PROF(34 + wg);
      const uint64_t dz = mkdesc(sb + OFF_U + wg * 4096, 1024, 128, 0);
      const uint64_t db2 = mkdesc(sb + OFF_T + T_B2, 128, 256, 0);
      mbar_wait(bars + 8 * BAR_T, 0);
      mbar_wait(bars + 8 * BAR_UH, 0);
      to_arr(a1[0], lds128(tb + T_A1));
      to_arr(a1[1], lds128(tb + T_A1 + 2048));
      wg_fence();
      s1(0);
      ldtw(0);
      ldtw(1);
      const uint32_t za = sb + (w < 2 ? OFF_U : OFF_H) + wg * 4096 + (w & 1) * 8192 + lane * 16;
      const uint32_t yl = (wtid ^ (4 * rank + wg)) * 16;
      const uint32_t yown = mapa(sb, rank) + yl, yrem = mapa(sb + OFF_LAND + wg * 2048, rank ^ 1) + yl;
      const uint32_t yb[2] = {mapa(bars + 8 * BAR_LAND, 0), mapa(bars + 8 * BAR_LAND, 1)};
      wg_wait<0>();
      fence_regs(d1);
      auto s4 = [&]() {
        wg_fence();
#pragma unroll
        for (int ks = 0; ks < 8; ks++) {
          const uint64_t d = dz + (ks & 1) * 128 + ((ks >> 1) & 1) * 512 + (ks >> 2) * ((OFF_H - OFF_U) >> 4);
          if (ks == 0) hmma_n64t<0>(d4, a4[ks], d);
          else hmma_n64t<1>(d4, a4[ks], d);
        }
        wg_commit();
      };
      auto e4 = [&](int pr) {
        fence_regs(d4);
        mbar_wait(bars + 8 * (pr == 0 ? BAR_LFREE : BAR_DEAD + 1), 0);
#pragma unroll
        for (int u = 0; u < 2; u++) {
          const int it = 2 * pr + u;
          const uint32_t o = (yown + y_slot(wg, it)) ^ (pr << 5), m = (yrem + it * 4096) ^ (pr << 5);
          st_async128(rank ? m : o, yb[0], d4[8 * u], d4[8 * u + 1], d4[8 * u + 2], d4[8 * u + 3]);
          st_async128(rank ? o : m, yb[1], d4[8 * u + 4], d4[8 * u + 5], d4[8 * u + 6], d4[8 * u + 7]);
        }
      };
      uint32_t a2[2][2][2][4], a3[2][2][4], d2[2][2][8], d3[2][8];
      auto s2a = [&]() {
        wg_fence();
#pragma unroll
        for (int c = 0; c < 4; c++) hmma_n32<0, 0>(d2[c & 1][c >> 1], a2[0][c & 1][c >> 1], db2 + (c >> 1) * 128);
      };
      auto s2b = [&]() {
        wg_fence();
#pragma unroll
        for (int c = 0; c < 4; c++) {
          hmma_n32<1, 0>(d2[c & 1][c >> 1], a2[1][c & 1][c >> 1], db2 + (c >> 1) * 128 + 64);
          if (c & 1) wg_commit();
        }
      };
      fft_e1<0>(d1, tw, a2[0]);
      s2a();
      fft_e1<1>(d1, tw, a2[1]);
      s2b();
      s1(1);
      ldtw(2);
      ldtw(3);
#pragma unroll
      for (int i = 0; i < 8; i++) to_arr(a4[i], lds128(tb + T_A4 + i * 2048));
#pragma unroll
      for (int it = 0; it < 4; it++) {
        if (it == 2) wg_wait<3>(); else if (it == 3) wg_wait<1>(); else wg_wait<2>();
        fence_regs(d2[0][0]);
        fence_regs(d2[1][0]);
        fft_e2<0, 0>(d2[0][0], d2[1][0], a3[0]);
        fft_e2<0, 1>(d2[0][0], d2[1][0], a3[1]);
        if (it == 2) wg_wait<2>(); else if (it == 3) wg_wait<0>(); else wg_wait<1>();
        fence_regs(d2[0][1]);
        fence_regs(d2[1][1]);
        fft_e2<1, 0>(d2[0][1], d2[1][1], a3[0]);
        fft_e2<1, 1>(d2[0][1], d2[1][1], a3[1]);
        wg_fence();
        hmma_n32<0, 0>(d3[0], a3[0][0], db2);
        hmma_n32<0, 0>(d3[1], a3[0][1], db2);
        hmma_n32<1, 0>(d3[0], a3[1][0], db2 + 64);
        hmma_n32<1, 0>(d3[1], a3[1][1], db2 + 64);
        wg_commit();
        if (it < 3) {
          wg_wait<1>();
          if (it == 2) {
            if (wtid == 64) mbar_arrive(bars + 8 * BAR_DEAD);
            e4(0);
          }
          fence_regs(d1);
          fft_e1<0>(d1, tw, a2[0]);
          s2a();
          wg_commit();
          wg_wait<1>();
        }
        if (ORD == 0 || it == 3) wg_wait<0>();
        if (it == 3 && wtid == 64) mbar_arrive(bars + 8 * (BAR_DEAD + 1));
        fence_regs(d3[0]);
        fence_regs(d3[1]);
        if (ORD == 0 && it < 3) s2a();
        fft_e3(d3, tw, za + (it & 1) * 512);
        if (ORD != 2 && it < 3) {
          fft_e1<1>(d1, tw, a2[1]);
          s2b();
        }
        if (it & 1) {
          fence_async_smem();
          nb_sync(NB_WG + wg, 128);
          if (it == 1 && signaller) mbar_arrive_cluster(rbars + 8 * BAR_LFREE);
          s4();
        }
        if (it < 2) s1(it + 2);
        if (w == 0) PROF3(40 + 4 * wg + it);
      }
      if (PEEL && MODE == 0) {
        mbar_wait(bars + 8 * BAR_FULL2, 0);
        g2_step(0, 0);
        wg_wait<1>();
      } else {
        wg_wait<0>();
      }
      if (signaller) mbar_arrive_cluster(rbars + 8 * (BAR_EMPTY2 + 4));
      e4(1);
      if (PEEL && MODE == 0) {
        wg_wait<0>();
        if (signaller) mbar_arrive_cluster(rbars + 8 * BAR_EMPTY2);
      }
      PROF(6 + wg);
    }
    }

    if (MODE != 1) {
      int s = PEEL && MODE == 0, ph = 0;
#pragma unroll 1
      for (int kb = s; kb < STAG; kb++) {
        mbar_wait(bars + 8 * (BAR_FULL2 + s), ph);
        if (kb == 1) PROF(8 + wg);
        if (warp == 4) PROF2(40 + kb);
        g2_step(s, kb);
        wg_wait<0>();
        if (kb < 16 - NS2 && signaller) mbar_arrive_cluster(rbars + 8 * (BAR_EMPTY2 + s));
        if (++s == NS2) { s = 0; ph ^= 1; }
      }
      if (STAG < 16) {
        if (wg == LAST) nb_sync(NB_LEAD, 256);
#pragma unroll
        for (int kb = STAG; kb < 16; kb++) {
          mbar_wait(bars + 8 * (BAR_FULL2 + kb % NS2), (kb / NS2) & 1);
          g2_step(kb % NS2, 1);
        }
        if (wg != LAST) nb_arrive(NB_LEAD, 256);
      }
      wg_wait<0>();
      fence_regs(acc);
      PROF(10 + wg);
      const int lr = lane & 7, lm = lane >> 3;
      const uint32_t wbase = sb + warp * 2048;
      const uint32_t base = wbase + (lr + 8 * (lm & 1)) * 128;
#pragma unroll
      for (int j = 0; j < 16; j += 2) {
        const uint32_t a = base + (j >> 3) * 16384 + ((((j & 7) + (lm >> 1)) ^ lr) << 4);
        stsm4(a, pack_bf16(acc[4 * j], acc[4 * j + 1]), pack_bf16(acc[4 * j + 2], acc[4 * j + 3]),
              pack_bf16(acc[4 * j + 4], acc[4 * j + 5]), pack_bf16(acc[4 * j + 6], acc[4 * j + 7]));
      }
      __syncwarp();
      {
        const int rr = lane >> 4, ck = lane & 7, hf = (lane >> 3) & 1;
        uint4* og = reinterpret_cast<uint4*>(p.out + (size_t)(2 * ((rb2 & 7) * 128 + warp * 16 + rr) + (rb2 >> 3)) * (2 * DM) + DM + cb2 * 128 + hf * 64 + ck * 8);
        uint4 v[8];
#pragma unroll
        for (int i = 0; i < 8; i++) v[i] = lds128(wbase + hf * 16384 + (2 * i + rr) * 128 + ((ck ^ ((2 * i + rr) & 7)) << 4));
#pragma unroll
        for (int i = 0; i < 8; i++) og[(size_t)i * 4 * (2 * DM / 8)] = v[i];
      }
      PROF(12 + wg);
    }
    cluster_sync_all();
  }
}

typedef CUresult (*EncodeFn)(CUtensorMap*, CUtensorMapDataType, cuuint32_t, void*, const cuuint64_t*, const cuuint64_t*,
                             const cuuint32_t*, const cuuint32_t*, CUtensorMapInterleave, CUtensorMapSwizzle,
                             CUtensorMapL2promotion, CUtensorMapFloatOOBfill);

void make_map(EncodeFn enc, CUtensorMap* tm, const void* base, int rank, const cuuint64_t* dims, const cuuint64_t* strides,
              const cuuint32_t* box, CUtensorMapSwizzle swz) {
  cuuint32_t es[5] = {1, 1, 1, 1, 1};
  enc(tm, CU_TENSOR_MAP_DATA_TYPE_BFLOAT16, rank, const_cast<void*>(base), dims, strides, box, es,
      CU_TENSOR_MAP_INTERLEAVE_NONE, swz, CU_TENSOR_MAP_L2_PROMOTION_L2_256B, CU_TENSOR_MAP_FLOAT_OOB_FILL_NONE);
}

}

extern "C" void kernel_launch(void* const* d_in, const int* in_sizes, int n_in, void* d_out, int out_size) {
  static EncodeFn enc = nullptr;
  static bool coresident = true;
  if (!enc) {
    void* fn = nullptr;
    cudaDriverEntryPointQueryResult qr;
    cudaGetDriverEntryPoint("cuTensorMapEncodeTiled", &fn, cudaEnableDefault, &qr);
    enc = (EncodeFn)fn;
    cudaFuncSetAttribute(fused_kernel<0>, cudaFuncAttributeMaxDynamicSharedMemorySize, SMEM_BYTES);
    cudaFuncSetAttribute(fused_kernel<1>, cudaFuncAttributeMaxDynamicSharedMemorySize, SMEM_BYTES);
    cudaFuncSetAttribute(fused_kernel<2>, cudaFuncAttributeMaxDynamicSharedMemorySize, SMEM_BYTES);
    cudaLaunchConfig_t cfg = {};
    cfg.gridDim = dim3(NCTA);
    cfg.blockDim = dim3(NTHREADS);
    cfg.dynamicSmemBytes = SMEM_BYTES;
    cudaLaunchAttribute at;
    at.id = cudaLaunchAttributeClusterDimension;
    at.val.clusterDim.x = 2;
    at.val.clusterDim.y = 1;
    at.val.clusterDim.z = 1;
    cfg.attrs = &at;
    cfg.numAttrs = 1;
    int nclusters = 0;
    if (cudaOccupancyMaxActiveClusters(&nclusters, fused_kernel<0>, &cfg) == cudaSuccess) coresident = nclusters >= NCTA / 2;
    (void)cudaGetLastError();
  }
  CUtensorMap tmX, tmW, tmWo, tmQ, tmXh, tmWh;
  {
    cuuint64_t dims[3] = {1024, 2, 1024};
    cuuint64_t str[2] = {2048, 4096};
    cuuint32_t box[3] = {64, 1, 128};
    make_map(enc, &tmX, d_in[6], 3, dims, str, box, CU_TENSOR_MAP_SWIZZLE_128B);
  }
  {
    cuuint64_t dims[3] = {1024, 1024, 3};
    cuuint64_t str[2] = {6144, 2048};
    cuuint32_t box[3] = {64, 32, 3};
    make_map(enc, &tmW, d_in[7], 3, dims, str, box, CU_TENSOR_MAP_SWIZZLE_128B);
  }
  {
    cuuint64_t dims[3] = {64, 1024, 16};
    cuuint64_t str[2] = {2048, 128};
    cuuint32_t box[3] = {64, 64, 2};
    make_map(enc, &tmWo, d_in[8], 3, dims, str, box, CU_TENSOR_MAP_SWIZZLE_128B);
  }
  {
    cuuint64_t dims[5] = {1024, 2, 2, 8, 64};
    cuuint64_t str[4] = {2048, 16 * 2048, 2 * 2048, 32 * 2048};
    cuuint32_t box[5] = {16, 2, 2, 8, 4};
    make_map(enc, &tmQ, d_in[0], 5, dims, str, box, CU_TENSOR_MAP_SWIZZLE_NONE);
  }
  {
    cuuint64_t dims[4] = {1024, 256, 2, 4};
    cuuint64_t str[3] = {4096, 2048, 256 * 4096};
    cuuint32_t box[4] = {64, 8, 2, 4};
    make_map(enc, &tmXh, d_in[6], 4, dims, str, box, CU_TENSOR_MAP_SWIZZLE_128B);
  }
  {
    cuuint64_t dims[3] = {64, 1024, 48};
    cuuint64_t str[2] = {6144, 128};
    cuuint32_t box[3] = {64, 64, 4};
    make_map(enc, &tmWh, d_in[7], 3, dims, str, box, CU_TENSOR_MAP_SWIZZLE_128B);
  }
  Params p;
  p.q = (const __nv_bfloat16*)d_in[0];
  p.k = (const __nv_bfloat16*)d_in[1];
  p.v = (const __nv_bfloat16*)d_in[2];
  p.shift_k = (const __nv_bfloat16*)d_in[3];
  p.ssm_k = (const __nv_bfloat16*)d_in[4];
  p.ssm_D = (const __nv_bfloat16*)d_in[5];
  p.x = (const __nv_bfloat16*)d_in[6];
  p.w = (const __nv_bfloat16*)d_in[7];
  p.wo = (const __nv_bfloat16*)d_in[8];
  p.out = (__nv_bfloat16*)d_out;
  if (coresident) {
    fused_kernel<0><<<NCTA, NTHREADS, SMEM_BYTES>>>(p, tmX, tmW, tmWo, tmQ, tmXh, tmWh);
  } else {
    fused_kernel<0><<<4, NTHREADS, SMEM_BYTES>>>(p, tmX, tmW, tmWo, tmQ, tmXh, tmWh);
    fused_kernel<1><<<NCTA, NTHREADS, SMEM_BYTES>>>(p, tmX, tmW, tmWo, tmQ, tmXh, tmWh);
    fused_kernel<2><<<NCTA, NTHREADS, SMEM_BYTES>>>(p, tmX, tmW, tmWo, tmQ, tmXh, tmWh);
  }
}
```

```cpp
#include <cuda_runtime.h>
#include <cuda.h>
#include <cuda_bf16.h>
#include <stdint.h>

namespace {

constexpr int SEQ = 2048;
constexpr int DM = 1024;
constexpr int NCTA = 132;
constexpr int NTHREADS = 384;

constexpr int STG1A = 32768;
constexpr int NS1A = 3;
constexpr int STG1B = 12288;
constexpr int NS1B = 5;
constexpr int OFF_1B = NS1A * STG1A;
constexpr int STG2 = 32768;
constexpr int NS2 = 5;
constexpr int STGH = 73728;
constexpr int OFF_VP = 0;
constexpr int OFF_KH = 1 * STG2;
constexpr int OFF_OP = 2 * STG2;
constexpr int OFF_Q = 3 * STG2;
constexpr int T_A4 = 0, T_TW = 16384, T_B2 = 24576, T_A1 = 28672, T_END = 32768;
constexpr int OFF_U = 163840;
constexpr int OFF_H = OFF_U + 32768;
constexpr int OFF_T = OFF_U - T_END;
constexpr int OFF_LAND = 4 * STG2;
constexpr int OFF_BAR = OFF_H + 32768;
constexpr int OFF_SC = OFF_BAR + 512;
constexpr int OFF_L0 = -2048;
constexpr int SMEM_BYTES = 2048 + OFF_BAR + 1024;
static_assert(OFF_T + T_A1 == OFF_1B + NS1B * STG1B && OFF_T + T_TW == OFF_1B + 4 * STG1B && OFF_LAND == OFF_T + T_A4, "layout");
static_assert(3 * STGH <= OFF_BAR && SMEM_BYTES <= 232448, "smem");

constexpr int BAR_FULLA = 0;
constexpr int BAR_EMPTYA = 3;
constexpr int BAR_FULLB = 6;
constexpr int BAR_EMPTYB = 11;
constexpr int BAR_FULL2 = 16;
constexpr int BAR_EMPTY2 = 21;
constexpr int BAR_T = 26;
constexpr int BAR_UH = 27;
constexpr int BAR_LFREE = 28;
constexpr int BAR_LAND = 29;
constexpr int BAR_U = 30;
constexpr int BAR_Q = 31;
constexpr int BAR_STG = 32;
constexpr int BAR_DEAD = 33;
constexpr int BAR_X = 35;
constexpr int BAR_REL = 36;

constexpr int NB_G1DONE = 1;
constexpr int NB_OREADY = 2;
constexpr int NB_WG = 4;
constexpr int NB_HELP3 = 6;
constexpr int NB_FIRST = 7;
constexpr int NB_LEAD = 8;

#define PACE 390u
#define PF0 20
#define PEEL 1
#define IDLEW 1
#define LA0 3
#define LA1 4
#define STAG 12
#define LAST 0
#define FINE 40
#define F4 1
#define TST 1
#define ORD 1
#define S1FIRST 0
#define REG_MATH 224
#define REG_HELP 56
constexpr int SPIN_LIMIT = 1 << 20;

__device__ __align__(1024) __nv_bfloat16 g_o[SEQ * DM];
__device__ __align__(128) uint32_t g_flag_o[256];
__device__ uint32_t g_flag_h[4];
__device__ uint4 g_halo[128 * 128];
__device__ __align__(128) const uint32_t g_tab[T_END / 4] = {
0x3c003c00,0x3bf13bff,0,0xafd6a648,0x3c003c00,0x3b993bce,0,0xb505b303,0x3c003c00,0x3af63b50,0,0xb7e3b67c,
0x3c003c00,0x3a0f3a8a,0,0xb93ab89b,0x3bc33bfe,0x3b773bfa,0xb3c6aa48,0xb5c2acb5,0x3a6d3b3b,0x389b3a4f,0xb8c4b6d7,0xba8ab8ec,
0x381d395f,0x26483505,0xbaddb9ed,0xbbffbb99,0x30b23564,0xb848b444,0xbbeabb88,0xbac2bbb6,0x3b0e3bf6,0x3a8a3bf1,0xb78bae46,0xb89bafd6,
0x34a53913,0xa6483732,0xbba8ba2f,0xbbffbb25,0xb78bae46,0xbac2b7e3,0xbb0ebbf6,0xb848baf6,0xbba8ba2f,0xbb50bbfa,0xb4a5b913,0x367cacb5,
0x39ed3bea,0x393a3be2,0xb95fb0b2,0xba0fb179,0xb56433c6,0xb8ec2648,0xbb88bbc3,0xba4fbbff,0xbbfeba6d,0xbb25bbce,0xaa48b8c4,0x3732b303,
0xb6d7badd,0x3444b67c,0x3b3b381d,0x3bb63b50,0x38723bd9,0x37323bce,0xbaa7b23e,0xbb25b303,0xbaa7b23e,0xbbb6b67c,0xb872bbd9,0xb444bb50,
0xb872bbd9,0xacb5ba8a,0x3aa7323e,0x3bfa389b,0x3aa7323e,0x3bf139cb,0x38723bd9,0xafd63984,0x35643bc3,0x33033bb6,0xbb88b3c6,0xbbceb444,
0xbbfeb8c4,0xbb77ba0f,0x2a48ba6d,0x35c2b93a,0x36d7b81d,0x3a8aafd6,0x3b3b3add,0x389b3bf1,0x395f3bea,0x26483b25,0xb9ed30b2,0xbbffb732,
0x2e463ba8,0xa6483b99,0xbbf6b4a5,0xbbffb505,0xba2fbb0e,0xb848bbb6,0x3913b78b,0x3ac2b444,0x3bf634a5,0x3b50393a,0x2e463ba8,0xb67c3a0f,
0xb913378b,0xbbe2afd6,0xba2fbb0e,0xb179bbf1,0xb0b23b88,0xb4443b77,0xbbeab564,0xbbb6b5c2,0xb3c6bbfe,0x2cb5bbe2,0x3bc3aa48,0x3bfa3179,
0x38c43b3b,0x2fd63bff,0xba6d36d7,0xbbf12648,0xbaddb95f,0xb505bbce,0x381db9ed,0x3b99b303,0xb61f3b64,0xb7e33b50,0xbb64b61f,0xbaf6b67c,
0x361fbb64,0x393aba8a,0x3b64361f,0x3a0f389b,0xb61f3b64,0xba4f3984,0xbb64b61f,0xb8ecb9cb,0x361fbb64,0x3b25b848,0x3b64361f,0x37323ac2,
0xb8c43b3b,0xb9843b25,0xba6db6d7,0xb9cbb732,0x3addb95f,0x3bceb7e3,0x381d39ed,0x33033af6,0xbbea3564,0xbb77acb5,0xb0b2bb88,0x35c2bbfa,
0x3bc32a48,0x389b38ec,0xb3c63bfe,0xba8a3a4f,0xba2f3b0e,0xbac23af6,0xb913b78b,0xb848b7e3,0x3bf6b4a5,0x3b50acb5,0xae463ba8,0xb67c3bfa,
0xb913b78b,0xb179ba4f,0x3a2fbb0e,0x3be2b8ec,0xae463ba8,0xb9cb3b99,0xbbf634a5,0xb984b505,0xbb3b3add,0xbb993ac2,0xb6d7b81d,0xb505b848,
0x39ed30b2,0x37e335c2,0xb95f3bea,0xbaf63b77,0x3564bbc3,0x3a0fbbe2,0x3b88b3c6,0x393a3179,0xbbfe38c4,0xba4f2648,0xaa48ba6d,0x38ecbbff,
0xbbd93aa7,0xbbfa3a8a,0xb23eb872,0xacb5b89b,0x323e3872,0xafd639cb,0xbbd93aa7,0xbbf13984,0x3bd9baa7,0x3b99b848,0x323e3872,0xb5053ac2,
0xb23eb872,0x37e3bb77,0x3bd9baa7,0x3af6b5c2,0xbbfe3a6d,0xbbe23a4f,0x2a48b8c4,0x3179b8ec,0xb6d73add,0xb9843b99,0xbb3b381d,0xb9cb3505,
0x395fb0b2,0x33033444,0xb9ed3bea,0xbbce3bb6,0x3b88bbc3,0x3b77b93a,0x356433c6,0xb5c23a0f,0xbba83a2f,0xbb503a0f,0x34a5b913,0x367cb93a,
0xbb0e3bf6,0xbbe23bf1,0xb78b2e46,0xb179afd6,0xb4a53913,0xb9cb3b25,0xbba83a2f,0xb9843732,0x378bae46,0xb30337e3,0xbb0e3bf6,0xbbce3af6,
0xbadd39ed,0xba4f39cb,0x381db95f,0x38ecb984,0xbbea3b88,0xbb253ac2,0x30b2b564,0x3732b848,0xbbc33bfe,0xbbb63b77,0xb3c62a48,0x3444b5c2,
0xba6d3b3b,0xbbfa3be2,0xb8c436d7,0x2cb5b179,0xb9a839a8,0xb8ec3984,0x39a8b9a8,0x3a4fb9cb,0xb9a839a8,0xb7323848,0x39a8b9a8,0x3b25bac2,
0xb9a839a8,0xb44435c2,0x39a8b9a8,0x3bb6bb77,0xb9a839a8,0xacb53179,0x39a8b9a8,0x3bfabbe2,0xb81d395f,0xb67c393a,0x3addb9ed,0x3b50ba0f,
0xb0b23564,0x31792fd6,0x3beabb88,0x3be2bbf1,0x33c6aa48,0x3984b732,0x3bc3bbfe,0x39cbbb25,0x38c4b6d7,0x3bcebaf6,0x3a6dbb3b,0x3303b7e3,
0xb4a53913,0xb17938ec,0x3ba8ba2f,0x3be2ba4f,0x378bae46,0x39cbb505,0x3b0ebbf6,0x3984bb99,0x3ba8ba2f,0x3bcebbb6,0x34a5b913,0xb303b444,
0x3b0ebbf6,0x35c2ba0f,0xb78b2e46,0xbb77393a,0xaa4838c4,0x2cb5389b,0x3bfeba6d,0x3bfaba8a,0x3b3bb81d,0x3bf1b984,0x36d7badd,0x2fd6b9cb,
0x39edbbea,0x3505bac2,0xb95f30b2,0xbb993848,0xb564b3c6,0xbaf635c2,0xbb883bc3,0xb7e33b77,0x323e3872,0x35053848,0x3bd9baa7,0x3b99bac2,
0x3bd9baa7,0x3af6bb77,0xb23eb872,0xb7e3b5c2,0xb23eb872,0xb93ab179,0xbbd93aa7,0xba0f3be2,0xbbd93aa7,0xb8ec3bff,0x323e3872,0x3a4fa648,
0x36d7381d,0x384837e3,0x3b3bbadd,0x3ac2baf6,0x395fbbea,0x367cbbfa,0xb9edb0b2,0xbb502cb5,0xbb8833c6,0xbbe238ec,0xb5643bc3,0x31793a4f,
0x2a483a6d,0x39843505,0x3bfeb8c4,0x39cbbb99,0x3913378b,0x39cb3732,0x3a2fbb0e,0x3984bb25,0x2e46bba8,0xb303baf6,0xbbf634a5,0xbbce37e3,
0xba2f3b0e,0xb5c23bfa,0x3913378b,0x3b772cb5,0x3bf6b4a5,0x3a8aba4f,0x2e46bba8,0xb89bb8ec,0x3a6d36d7,0x3af6367c,0x38c4bb3b,0x37e3bb50,
0xb81db9ed,0xba0fb89b,0xbadd395f,0xb93a3a8a,0x30b23b88,0x38ec39cb,0x3beab564,0x3a4fb984,0x33c6bbfe,0xb732bac2,0xbbc3aa48,0xbb253848,
0x3b64361f,0x3bb635c2,0x361fbb64,0x3444bb77,0xbb64b61f,0xbbfab179,0xb61f3b64,0xacb53be2,0x3b64361f,0x3bf1a648,0x361fbb64,0xafd6bbff,
0xbb64b61f,0xbb993303,0xb61f3b64,0x35053bce,0x3bea3564,0x3bff3505,0x30b2bb88,0x2648bb99,0xbbc32a48,0xbac23444,0x33c63bfe,0x38483bb6,
0x3a6db6d7,0x367cba0f,0xb8c4bb3b,0xbb50b93a,0xb81d39ed,0x31793bf1,0x3add395f,0x3be22fd6,0x3bf634a5,0x3bce3444,0xae46bba8,0xb303bbb6,
0xb913378b,0xb5c2393a,0x3a2f3b0e,0x3b773a0f,0xae46bba8,0xb89bbbf1,0xbbf6b4a5,0xba8a2fd6,0x3a2f3b0e,0x3bff3732,0x3913b78b,0xa648bb25,
0x3b8833c6,0x3b253303,0xb564bbc3,0xb732bbce,0xaa483a6d,0x34443b50,0x3bfe38c4,0x3bb6367c,0xbb3bbadd,0xbbfab89b,0xb6d7381d,0x2cb53a8a,
0x39edb0b2,0x2fd6b984,0xb95fbbea,0xbbf1b9cb,0x3aa7323e,0x3a0f3179,0xb872bbd9,0xb93abbe2,0x38723bd9,0x3a4f3bff,0x3aa7323e,0x38eca648,
0xbaa7b23e,0xb7323303,0x38723bd9,0x3b253bce,0xb872bbd9,0xbbb6bb50,0xbaa7b23e,0xb444367c,0x395f30b2,0x389b2fd6,0xb9edbbea,0xba8abbf1,
0x3b883bc3,0x3bff3b25,0x3564b3c6,0x2648b732,0x2a4838c4,0x38483af6,0x3bfe3a6d,0x3ac237e3,0xbb3bb81d,0xb67c2cb5,0x36d73add,0x3b503bfa,
0x378b2e46,0x35c22cb5,0xbb0ebbf6,0xbb77bbfa,0x3ba83a2f,0x3a8a38ec,0xb4a5b913,0xb89bba4f,0x3b0e3bf6,0x3bff3b99,0x378b2e46,0xa648b505,
0x34a53913,0x3ac23bb6,0x3ba83a2f,0x38483444,0x33c62a48,0x2fd62648,0xbbc3bbfe,0xbbf1bbff,0x38c436d7,0x35053303,0xba6dbb3b,0xbb99bbce,
0x3add39ed,0x37e3367c,0xb81db95f,0xbaf6bb50,0x3bea3b88,0x393a389b,0xb0b2b564,0xba0fba8a,0x3c003c00,0xbbf1bbff,0,0x2fd62648,
0x3c003c00,0xbb99bbce,0,0x35053303,0x3c003c00,0xbaf6bb50,0,0x37e3367c,0x3c003c00,0xba0fba8a,0,0x393a389b,
0x3bc33bfe,0xbb77bbfa,0xb3c6aa48,0x35c22cb5,0x3a6d3b3b,0xb89bba4f,0xb8c4b6d7,0x3a8a38ec,0x381d395f,0xa648b505,0xbaddb9ed,0x3bff3b99,
0x30b23564,0x38483444,0xbbeabb88,0x3ac23bb6,0x3b0e3bf6,0xba8abbf1,0xb78bae46,0x389b2fd6,0x34a53913,0x2648b732,0xbba8ba2f,0x3bff3b25,
0xb78bae46,0x3ac237e3,0xbb0ebbf6,0x38483af6,0xbba8ba2f,0x3b503bfa,0xb4a5b913,0xb67c2cb5,0x39ed3bea,0xb93abbe2,0xb95fb0b2,0x3a0f3179,
0xb56433c6,0x38eca648,0xbb88bbc3,0x3a4f3bff,0xbbfeba6d,0x3b253bce,0xaa48b8c4,0xb7323303,0xb6d7badd,0xb444367c,0x3b3b381d,0xbbb6bb50,
0x38723bd9,0xb732bbce,0xbaa7b23e,0x3b253303,0xbaa7b23e,0x3bb6367c,0xb872bbd9,0x34443b50,0xb872bbd9,0x2cb53a8a,0x3aa7323e,0xbbfab89b,
0x3aa7323e,0xbbf1b9cb,0x38723bd9,0x2fd6b984,0x35643bc3,0xb303bbb6,0xbb88b3c6,0x3bce3444,0xbbfeb8c4,0x3b773a0f,0x2a48ba6d,0xb5c2393a,
0x36d7b81d,0xba8a2fd6,0x3b3b3add,0xb89bbbf1,0x395f3bea,0xa648bb25,0xb9ed30b2,0x3bff3732,0x2e463ba8,0x2648bb99,0xbbf6b4a5,0x3bff3505,
0xba2fbb0e,0x38483bb6,0x3913b78b,0xbac23444,0x3bf634a5,0xbb50b93a,0x2e463ba8,0x367cba0f,0xb913378b,0x3be22fd6,0xba2fbb0e,0x31793bf1,
0xb0b23b88,0x3444bb77,0xbbeab564,0x3bb635c2,0xb3c6bbfe,0xacb53be2,0x3bc3aa48,0xbbfab179,0x38c43b3b,0xafd6bbff,0xba6d36d7,0x3bf1a648,
0xbaddb95f,0x35053bce,0x381db9ed,0xbb993303,0xb61f3b64,0x37e3bb50,0xbb64b61f,0x3af6367c,0x361fbb64,0xb93a3a8a,0x3b64361f,0xba0fb89b,
0xb61f3b64,0x3a4fb984,0xbb64b61f,0x38ec39cb,0x361fbb64,0xbb253848,0x3b64361f,0xb732bac2,0xb8c43b3b,0x3984bb25,0xba6db6d7,0x39cb3732,
0x3addb95f,0xbbce37e3,0x381d39ed,0xb303baf6,0xbbea3564,0x3b772cb5,0xb0b2bb88,0xb5c23bfa,0x3bc32a48,0xb89bb8ec,0xb3c63bfe,0x3a8aba4f,
0xba2f3b0e,0x3ac2baf6,0xb913b78b,0x384837e3,0x3bf6b4a5,0xbb502cb5,0xae463ba8,0x367cbbfa,0xb913b78b,0x31793a4f,0x3a2fbb0e,0xbbe238ec,
0xae463ba8,0x39cbbb99,0xbbf634a5,0x39843505,0xbb3b3add,0x3b99bac2,0xb6d7b81d,0x35053848,0x39ed30b2,0xb7e3b5c2,0xb95f3bea,0x3af6bb77,
0x3564bbc3,0xba0f3be2,0x3b88b3c6,0xb93ab179,0xbbfe38c4,0x3a4fa648,0xaa48ba6d,0xb8ec3bff,0xbbd93aa7,0x3bfaba8a,0xb23eb872,0x2cb5389b,
0x323e3872,0x2fd6b9cb,0xbbd93aa7,0x3bf1b984,0x3bd9baa7,0xbb993848,0x323e3872,0x3505bac2,0xb23eb872,0xb7e33b77,0x3bd9baa7,0xbaf635c2,
0xbbfe3a6d,0x3be2ba4f,0x2a48b8c4,0xb17938ec,0xb6d73add,0x3984bb99,0xbb3b381d,0x39cbb505,0x395fb0b2,0xb303b444,0xb9ed3bea,0x3bcebbb6,
0x3b88bbc3,0xbb77393a,0x356433c6,0x35c2ba0f,0xbba83a2f,0x3b50ba0f,0x34a5b913,0xb67c393a,0xbb0e3bf6,0x3be2bbf1,0xb78b2e46,0x31792fd6,
0xb4a53913,0x39cbbb25,0xbba83a2f,0x3984b732,0x378bae46,0x3303b7e3,0xbb0e3bf6,0x3bcebaf6,0xbadd39ed,0x3a4fb9cb,0x381db95f,0xb8ec3984,
0xbbea3b88,0x3b25bac2,0x30b2b564,0xb7323848,0xbbc33bfe,0x3bb6bb77,0xb3c62a48,0xb44435c2,0xba6d3b3b,0x3bfabbe2,0xb8c436d7,0xacb53179,
0xb9a839a8,0x38ecb984,0x39a8b9a8,0xba4f39cb,0xb9a839a8,0x3732b848,0x39a8b9a8,0xbb253ac2,0xb9a839a8,0x3444b5c2,0x39a8b9a8,0xbbb63b77,
0xb9a839a8,0x2cb5b179,0x39a8b9a8,0xbbfa3be2,0xb81d395f,0x367cb93a,0x3addb9ed,0xbb503a0f,0xb0b23564,0xb179afd6,0x3beabb88,0xbbe23bf1,
0x33c6aa48,0xb9843732,0x3bc3bbfe,0xb9cb3b25,0x38c4b6d7,0xbbce3af6,0x3a6dbb3b,0xb30337e3,0xb4a53913,0x3179b8ec,0x3ba8ba2f,0xbbe23a4f,
0x378bae46,0xb9cb3505,0x3b0ebbf6,0xb9843b99,0x3ba8ba2f,0xbbce3bb6,0x34a5b913,0x33033444,0x3b0ebbf6,0xb5c23a0f,0xb78b2e46,0x3b77b93a,
0xaa4838c4,0xacb5b89b,0x3bfeba6d,0xbbfa3a8a,0x3b3bb81d,0xbbf13984,0x36d7badd,0xafd639cb,0x39edbbea,0xb5053ac2,0xb95f30b2,0x3b99b848,
0xb564b3c6,0x3af6b5c2,0xbb883bc3,0x37e3bb77,0x323e3872,0xb505b848,0x3bd9baa7,0xbb993ac2,0x3bd9baa7,0xbaf63b77,0xb23eb872,0x37e335c2,
0xb23eb872,0x393a3179,0xbbd93aa7,0x3a0fbbe2,0xbbd93aa7,0x38ecbbff,0x323e3872,0xba4f2648,0x36d7381d,0xb848b7e3,0x3b3bbadd,0xbac23af6,
0x395fbbea,0xb67c3bfa,0xb9edb0b2,0x3b50acb5,0xbb8833c6,0x3be2b8ec,0xb5643bc3,0xb179ba4f,0x2a483a6d,0xb984b505,0x3bfeb8c4,0xb9cb3b99,
0x3913378b,0xb9cbb732,0x3a2fbb0e,0xb9843b25,0x2e46bba8,0x33033af6,0xbbf634a5,0x3bceb7e3,0xba2f3b0e,0x35c2bbfa,0x3913378b,0xbb77acb5,
0x3bf6b4a5,0xba8a3a4f,0x2e46bba8,0x389b38ec,0x3a6d36d7,0xbaf6b67c,0x38c4bb3b,0xb7e33b50,0xb81db9ed,0x3a0f389b,0xbadd395f,0x393aba8a,
0x30b23b88,0xb8ecb9cb,0x3beab564,0xba4f3984,0x33c6bbfe,0x37323ac2,0xbbc3aa48,0x3b25b848,0x3b64361f,0xbbb6b5c2,0x361fbb64,0xb4443b77,
0xbb64b61f,0x3bfa3179,0xb61f3b64,0x2cb5bbe2,0x3b64361f,0xbbf12648,0x361fbb64,0x2fd63bff,0xbb64b61f,0x3b99b303,0xb61f3b64,0xb505bbce,
0x3bea3564,0xbbffb505,0x30b2bb88,0xa6483b99,0xbbc32a48,0x3ac2b444,0x33c63bfe,0xb848bbb6,0x3a6db6d7,0xb67c3a0f,0xb8c4bb3b,0x3b50393a,
0xb81d39ed,0xb179bbf1,0x3add395f,0xbbe2afd6,0x3bf634a5,0xbbceb444,0xae46bba8,0x33033bb6,0xb913378b,0x35c2b93a,0x3a2f3b0e,0xbb77ba0f,
0xae46bba8,0x389b3bf1,0xbbf6b4a5,0x3a8aafd6,0x3a2f3b0e,0xbbffb732,0x3913b78b,0x26483b25,0x3b8833c6,0xbb25b303,0xb564bbc3,0x37323bce,
0xaa483a6d,0xb444bb50,0x3bfe38c4,0xbbb6b67c,0xbb3bbadd,0x3bfa389b,0xb6d7381d,0xacb5ba8a,0x39edb0b2,0xafd63984,0xb95fbbea,0x3bf139cb,
0x3aa7323e,0xba0fb179,0xb872bbd9,0x393a3be2,0x38723bd9,0xba4fbbff,0x3aa7323e,0xb8ec2648,0xbaa7b23e,0x3732b303,0x38723bd9,0xbb25bbce,
0xb872bbd9,0x3bb63b50,0xbaa7b23e,0x3444b67c,0x395f30b2,0xb89bafd6,0xb9edbbea,0x3a8a3bf1,0x3b883bc3,0xbbffbb25,0x3564b3c6,0xa6483732,
0x2a4838c4,0xb848baf6,0x3bfe3a6d,0xbac2b7e3,0xbb3bb81d,0x367cacb5,0x36d73add,0xbb50bbfa,0x378b2e46,0xb5c2acb5,0xbb0ebbf6,0x3b773bfa,
0x3ba83a2f,0xba8ab8ec,0xb4a5b913,0x389b3a4f,0x3b0e3bf6,0xbbffbb99,0x378b2e46,0x26483505,0x34a53913,0xbac2bbb6,0x3ba83a2f,0xb848b444,
0x33c62a48,0xafd6a648,0xbbc3bbfe,0x3bf13bff,0x38c436d7,0xb505b303,0xba6dbb3b,0x3b993bce,0x3add39ed,0xb7e3b67c,0xb81db95f,0x3af63b50,
0x3bea3b88,0xb93ab89b,0xb0b2b564,0x3a0f3a8a,0x3c003c00,0x38ec3984,0,0xba4fb9cb,0x3c003c00,0x37323848,0,0xbb25bac2,
0x3c003c00,0x344435c2,0,0xbbb6bb77,0x3c003c00,0x2cb53179,0,0xbbfabbe2,0xb3c6aa48,0xbb50ba0f,0xbbc3bbfe,0xb67cb93a,
0xb8c4b6d7,0xbbe2bbf1,0xba6dbb3b,0x3179afd6,0xbaddb9ed,0xb9cbbb25,0xb81db95f,0x39843732,0xbbeabb88,0xb303b7e3,0xb0b2b564,0x3bce3af6,
0xbb0ebbf6,0xb179b8ec,0x378b2e46,0x3be23a4f,0xb4a5b913,0x39cb3505,0x3ba83a2f,0x39843b99,0x378b2e46,0x3bce3bb6,0x3b0e3bf6,0xb3033444,
0x3ba83a2f,0x35c23a0f,0x34a53913,0xbb77b93a,0x395f30b2,0x3bfa3a8a,0x39ed3bea,0xacb5389b,0x3b883bc3,0x2fd639cb,0xb56433c6,0xbbf1b984,
0x2a4838c4,0xbb99b848,0xbbfeba6d,0xb505bac2,0xbb3bb81d,0xb7e3bb77,0xb6d7badd,0x3af635c2,0x38723bd9,0xb5053848,0xbaa7b23e,0xbb99bac2,
0xbaa7b23e,0xbaf6bb77,0xb872bbd9,0x37e3b5c2,0xb872bbd9,0x393ab179,0x3aa7323e,0x3a0f3be2,0x3aa7323e,0x38ec3bff,0x38723bd9,0xba4fa648,
0xbb88b3c6,0xbac2baf6,0xb564bbc3,0x3848b7e3,0x2a48ba6d,0x3b502cb5,0x3bfe38c4,0x367c3bfa,0x3b3b3add,0xb1793a4f,0xb6d7381d,0xbbe2b8ec,
0xb9ed30b2,0xb9cbbb99,0xb95fbbea,0x3984b505,0xae46bba8,0x39cbb732,0x3bf634a5,0x39843b25,0x3a2f3b0e,0xb3033af6,0xb913378b,0xbbceb7e3,
0xbbf6b4a5,0xb5c2bbfa,0xae46bba8,0x3b77acb5,0x3913b78b,0x3a8a3a4f,0x3a2f3b0e,0xb89b38ec,0x3bea3564,0x37e33b50,0xb0b23b88,0xbaf6367c,
0xbbc32a48,0xb93aba8a,0xb3c6bbfe,0x3a0fb89b,0x3a6db6d7,0x3a4f3984,0x38c43b3b,0xb8ec39cb,0xb81d39ed,0xbb25b848,0xbaddb95f,0x3732bac2,
0xb61f3b64,0xbbb635c2,0xbb64b61f,0xb444bb77,0x361fbb64,0x3bfab179,0x3b64361f,0x2cb53be2,0xb61f3b64,0xbbf1a648,0xbb64b61f,0x2fd6bbff,
0x361fbb64,0x3b993303,0x3b64361f,0xb5053bce,0xba6db6d7,0xa648bb99,0x38c4bb3b,0x3bffb505,0x381d39ed,0xb8483bb6,0xbadd395f,0xbac2b444,
0xb0b2bb88,0x3b50b93a,0x3beab564,0x367c3a0f,0xb3c63bfe,0xbbe22fd6,0xbbc3aa48,0x3179bbf1,0x3a2fbb0e,0x3bceb444,0x3913378b,0xb3033bb6,
0xbbf634a5,0xb5c2b93a,0x2e46bba8,0x3b77ba0f,0x3913378b,0xb89b3bf1,0xba2f3b0e,0xba8aafd6,0x2e46bba8,0x3bffb732,0x3bf6b4a5,0xa6483b25,
0x36d7381d,0xb7323bce,0xbb3b3add,0xbb253303,0x395fbbea,0x3bb6b67c,0x39ed30b2,0xb4443b50,0xbb8833c6,0x2cb5ba8a,0x3564bbc3,0x3bfab89b,
0x2a483a6d,0xbbf139cb,0xbbfe38c4,0xafd6b984,0xbbd93aa7,0xba0f3179,0xb23eb872,0x393abbe2,0x323e3872,0xba4f3bff,0xbbd93aa7,0xb8eca648,
0x3bd9baa7,0x37323303,0x323e3872,0xbb253bce,0xb23eb872,0x3bb6bb50,0x3bd9baa7,0x3444367c,0x2a48b8c4,0x3a8abbf1,0x3bfeba6d,0x389bafd6,
0xbb3b381d,0xa648b732,0x36d7badd,0x3bffbb25,0xb9ed3bea,0xbac237e3,0xb95f30b2,0x3848baf6,0x356433c6,0xbb503bfa,0xbb883bc3,0xb67cacb5,
0x3ba8ba2f,0x35c2acb5,0xb4a53913,0xbb773bfa,0x3b0ebbf6,0x3a8ab8ec,0x378bae46,0xb89b3a4f,0x34a5b913,0x3bffbb99,0x3ba8ba2f,0xa6483505,
0xb78b2e46,0x3ac2bbb6,0x3b0ebbf6,0x3848b444,0xb81d395f,0xbbf13bff,0xbadd39ed,0xafd62648,0xb0b23564,0xbb993bce,0xbbea3b88,0xb5053303,
0x33c6aa48,0xbaf63b50,0xbbc33bfe,0xb7e3367c,0x38c4b6d7,0xba0f3a8a,0xba6d3b3b,0xb93a389b,0xb9a839a8,0x2fd6a648,0x39a8b9a8,0x3bf1bbff,
0xb9a839a8,0x3505b303,0x39a8b9a8,0x3b99bbce,0xb9a839a8,0x37e3b67c,0x39a8b9a8,0x3af6bb50,0xb9a839a8,0x393ab89b,0x39a8b9a8,0x3a0fba8a,
0x3addb9ed,0x3b77bbfa,0x381db95f,0xb5c22cb5,0x3beabb88,0x389bba4f,0x30b2b564,0xba8a38ec,0x3bc3bbfe,0x2648b505,0xb3c62a48,0xbbff3b99,
0x3a6dbb3b,0xb8483444,0xb8c436d7,0xbac23bb6,0x34a5b913,0xb89b2fd6,0xbba83a2f,0xba8a3bf1,0xb78b2e46,0xbbff3b25,0xbb0e3bf6,0x26483732,
0xbba83a2f,0xb8483af6,0xb4a53913,0x3ac2b7e3,0xbb0e3bf6,0x367c2cb5,0x378bae46,0x3b50bbfa,0xbbfe3a6d,0xb93a3be2,0xaa4838c4,0x3a0fb179,
0xb6d73add,0x38ec2648,0x3b3bb81d,0x3a4fbbff,0x395fb0b2,0x3b25bbce,0x39edbbea,0xb732b303,0x3b88bbc3,0xb444b67c,0xb564b3c6,0xbbb63b50,
0x323e3872,0x3b25b303,0x3bd9baa7,0x3732bbce,0x3bd9baa7,0x3444bb50,0xb23eb872,0xbbb6367c,0xb23eb872,0xbbfa389b,0xbbd93aa7,0xacb53a8a,
0xbbd93aa7,0x2fd63984,0x323e3872,0x3bf1b9cb,0x3b3bbadd,0x3303bbb6,0xb6d7b81d,0xbbce3444,0xb9edb0b2,0xbb773a0f,0xb95f3bea,0x35c2393a,
0xb5643bc3,0x3a8a2fd6,0x3b88b3c6,0x389bbbf1,0x3bfeb8c4,0x2648bb25,0xaa48ba6d,0xbbff3732,0xb913b78b,0xbbff3505,0xba2f3b0e,0x26483b99,
0xae463ba8,0x3ac23444,0x3bf6b4a5,0x3848bbb6,0x3a2fbb0e,0xb67cba0f,0xb913b78b,0xbb50393a,0xbbf634a5,0xb1793bf1,0xae463ba8,0x3be2afd6,
0xb8c43b3b,0x34443b77,0x3a6d36d7,0x3bb6b5c2,0x3addb95f,0xacb5bbe2,0xb81db9ed,0xbbfa3179,0xbbea3564,0xafd63bff,0x30b23b88,0x3bf12648,
0x3bc32a48,0x3505bbce,0x33c6bbfe,0xbb99b303,0x3b64361f,0x3af6b67c,0x361fbb64,0xb7e3bb50,0xbb64b61f,0xba0f389b,0xb61f3b64,0x393a3a8a,
0x3b64361f,0x38ecb9cb,0x361fbb64,0xba4fb984,0xbb64b61f,0xb7323ac2,0xb61f3b64,0x3b253848,0x30b2bb88,0xb984bb25,0xbbeab564,0xb9cb3732,
0x33c63bfe,0x3bce37e3,0x3bc3aa48,0x3303baf6,0xb8c4bb3b,0xbb772cb5,0xba6d36d7,0x35c23bfa,0x3add395f,0x389bb8ec,0x381db9ed,0xba8aba4f,
0xbbf6b4a5,0xb84837e3,0x2e463ba8,0x3ac23af6,0x3913b78b,0xb67cbbfa,0xba2fbb0e,0xbb50acb5,0x2e463ba8,0x3be238ec,0x3bf634a5,0x3179ba4f,
0xba2fbb0e,0xb9843505,0xb913378b,0x39cb3b99,0x35643bc3,0x3b993ac2,0x3b8833c6,0x3505b848,0xbbfeb8c4,0xb7e335c2,0xaa483a6d,0x3af63b77,
0x36d7b81d,0xba0fbbe2,0xbb3bbadd,0xb93a3179,0x395f3bea,0x3a4f2648,0x39edb0b2,0xb8ecbbff,0x3aa7323e,0x2cb5b89b,0xb872bbd9,0xbbfaba8a,
0x38723bd9,0x3bf13984,0x3aa7323e,0xafd6b9cb,0xbaa7b23e,0x35053ac2,0x38723bd9,0x3b993848,0xb872bbd9,0xbaf6b5c2,0xbaa7b23e,0x37e33b77,
0xb9edbbea,0xbbe2ba4f,0xb95fb0b2,0x317938ec,0x3564b3c6,0xb984bb99,0xbb88bbc3,0xb9cbb505,0x3bfe3a6d,0x3303b444,0xaa48b8c4,0xbbcebbb6,
0x36d73add,0x3b77393a,0x3b3b381d,0xb5c2ba0f,0xb78bae46,0x367c393a,0x3b0e3bf6,0x3b503a0f,0xbba8ba2f,0xb1792fd6,0x34a53913,0x3be23bf1,
0xbb0ebbf6,0xb984b732,0xb78bae46,0x39cb3b25,0xb4a5b913,0xbbcebaf6,0xbba8ba2f,0x330337e3,0x3bc33bfe,0x3a4f39cb,0x33c62a48,0xb8ecb984,
0x3a6d3b3b,0x3b253ac2,0x38c436d7,0xb732b848,0x381d395f,0x3bb63b77,0x3add39ed,0xb444b5c2,0x30b23564,0x3bfa3be2,0x3bea3b88,0xacb5b179,
0x3c003c00,0xb8ecb984,0,0x3a4f39cb,0x3c003c00,0xb732b848,0,0x3b253ac2,0x3c003c00,0xb444b5c2,0,0x3bb63b77,
0x3c003c00,0xacb5b179,0,0x3bfa3be2,0xb3c6aa48,0x3b503a0f,0xbbc3bbfe,0x367c393a,0xb8c4b6d7,0x3be23bf1,0xba6dbb3b,0xb1792fd6,
0xbaddb9ed,0x39cb3b25,0xb81db95f,0xb984b732,0xbbeabb88,0x330337e3,0xb0b2b564,0xbbcebaf6,0xbb0ebbf6,0x317938ec,0x378b2e46,0xbbe2ba4f,
0xb4a5b913,0xb9cbb505,0x3ba83a2f,0xb984bb99,0x378b2e46,0xbbcebbb6,0x3b0e3bf6,0x3303b444,0x3ba83a2f,0xb5c2ba0f,0x34a53913,0x3b77393a,
0x395f30b2,0xbbfaba8a,0x39ed3bea,0x2cb5b89b,0x3b883bc3,0xafd6b9cb,0xb56433c6,0x3bf13984,0x2a4838c4,0x3b993848,0xbbfeba6d,0x35053ac2,
0xbb3bb81d,0x37e33b77,0xb6d7badd,0xbaf6b5c2,0x38723bd9,0x3505b848,0xbaa7b23e,0x3b993ac2,0xbaa7b23e,0x3af63b77,0xb872bbd9,0xb7e335c2,
0xb872bbd9,0xb93a3179,0x3aa7323e,0xba0fbbe2,0x3aa7323e,0xb8ecbbff,0x38723bd9,0x3a4f2648,0xbb88b3c6,0x3ac23af6,0xb564bbc3,0xb84837e3,
0x2a48ba6d,0xbb50acb5,0x3bfe38c4,0xb67cbbfa,0x3b3b3add,0x3179ba4f,0xb6d7381d,0x3be238ec,0xb9ed30b2,0x39cb3b99,0xb95fbbea,0xb9843505,
0xae46bba8,0xb9cb3732,0x3bf634a5,0xb984bb25,0x3a2f3b0e,0x3303baf6,0xb913378b,0x3bce37e3,0xbbf6b4a5,0x35c23bfa,0xae46bba8,0xbb772cb5,
0x3913b78b,0xba8aba4f,0x3a2f3b0e,0x389bb8ec,0x3bea3564,0xb7e3bb50,0xb0b23b88,0x3af6b67c,0xbbc32a48,0x393a3a8a,0xb3c6bbfe,0xba0f389b,
0x3a6db6d7,0xba4fb984,0x38c43b3b,0x38ecb9cb,0xb81d39ed,0x3b253848,0xbaddb95f,0xb7323ac2,0xb61f3b64,0x3bb6b5c2,0xbb64b61f,0x34443b77,
0x361fbb64,0xbbfa3179,0x3b64361f,0xacb5bbe2,0xb61f3b64,0x3bf12648,0xbb64b61f,0xafd63bff,0x361fbb64,0xbb99b303,0x3b64361f,0x3505bbce,
0xba6db6d7,0x26483b99,0x38c4bb3b,0xbbff3505,0x381d39ed,0x3848bbb6,0xbadd395f,0x3ac23444,0xb0b2bb88,0xbb50393a,0x3beab564,0xb67cba0f,
0xb3c63bfe,0x3be2afd6,0xbbc3aa48,0xb1793bf1,0x3a2fbb0e,0xbbce3444,0x3913378b,0x3303bbb6,0xbbf634a5,0x35c2393a,0x2e46bba8,0xbb773a0f,
0x3913378b,0x389bbbf1,0xba2f3b0e,0x3a8a2fd6,0x2e46bba8,0xbbff3732,0x3bf6b4a5,0x2648bb25,0x36d7381d,0x3732bbce,0xbb3b3add,0x3b25b303,
0x395fbbea,0xbbb6367c,0x39ed30b2,0x3444bb50,0xbb8833c6,0xacb53a8a,0x3564bbc3,0xbbfa389b,0x2a483a6d,0x3bf1b9cb,0xbbfe38c4,0x2fd63984,
0xbbd93aa7,0x3a0fb179,0xb23eb872,0xb93a3be2,0x323e3872,0x3a4fbbff,0xbbd93aa7,0x38ec2648,0x3bd9baa7,0xb732b303,0x323e3872,0x3b25bbce,
0xb23eb872,0xbbb63b50,0x3bd9baa7,0xb444b67c,0x2a48b8c4,0xba8a3bf1,0x3bfeba6d,0xb89b2fd6,0xbb3b381d,0x26483732,0x36d7badd,0xbbff3b25,
0xb9ed3bea,0x3ac2b7e3,0xb95f30b2,0xb8483af6,0x356433c6,0x3b50bbfa,0xbb883bc3,0x367c2cb5,0x3ba8ba2f,0xb5c22cb5,0xb4a53913,0x3b77bbfa,
0x3b0ebbf6,0xba8a38ec,0x378bae46,0x389bba4f,0x34a5b913,0xbbff3b99,0x3ba8ba2f,0x2648b505,0xb78b2e46,0xbac23bb6,0x3b0ebbf6,0xb8483444,
0xb81d395f,0x3bf1bbff,0xbadd39ed,0x2fd6a648,0xb0b23564,0x3b99bbce,0xbbea3b88,0x3505b303,0x33c6aa48,0x3af6bb50,0xbbc33bfe,0x37e3b67c,
0x38c4b6d7,0x3a0fba8a,0xba6d3b3b,0x393ab89b,0xb9a839a8,0xafd62648,0x39a8b9a8,0xbbf13bff,0xb9a839a8,0xb5053303,0x39a8b9a8,0xbb993bce,
0xb9a839a8,0xb7e3367c,0x39a8b9a8,0xbaf63b50,0xb9a839a8,0xb93a389b,0x39a8b9a8,0xba0f3a8a,0x3addb9ed,0xbb773bfa,0x381db95f,0x35c2acb5,
0x3beabb88,0xb89b3a4f,0x30b2b564,0x3a8ab8ec,0x3bc3bbfe,0xa6483505,0xb3c62a48,0x3bffbb99,0x3a6dbb3b,0x3848b444,0xb8c436d7,0x3ac2bbb6,
0x34a5b913,0x389bafd6,0xbba83a2f,0x3a8abbf1,0xb78b2e46,0x3bffbb25,0xbb0e3bf6,0xa648b732,0xbba83a2f,0x3848baf6,0xb4a53913,0xbac237e3,
0xbb0e3bf6,0xb67cacb5,0x378bae46,0xbb503bfa,0xbbfe3a6d,0x393abbe2,0xaa4838c4,0xba0f3179,0xb6d73add,0xb8eca648,0x3b3bb81d,0xba4f3bff,
0x395fb0b2,0xbb253bce,0x39edbbea,0x37323303,0x3b88bbc3,0x3444367c,0xb564b3c6,0x3bb6bb50,0x323e3872,0xbb253303,0x3bd9baa7,0xb7323bce,
0x3bd9baa7,0xb4443b50,0xb23eb872,0x3bb6b67c,0xb23eb872,0x3bfab89b,0xbbd93aa7,0x2cb5ba8a,0xbbd93aa7,0xafd6b984,0x323e3872,0xbbf139cb,
0x3b3bbadd,0xb3033bb6,0xb6d7b81d,0x3bceb444,0xb9edb0b2,0x3b77ba0f,0xb95f3bea,0xb5c2b93a,0xb5643bc3,0xba8aafd6,0x3b88b3c6,0xb89b3bf1,
0x3bfeb8c4,0xa6483b25,0xaa48ba6d,0x3bffb732,0xb913b78b,0x3bffb505,0xba2f3b0e,0xa648bb99,0xae463ba8,0xbac2b444,0x3bf6b4a5,0xb8483bb6,
0x3a2fbb0e,0x367c3a0f,0xb913b78b,0x3b50b93a,0xbbf634a5,0x3179bbf1,0xae463ba8,0xbbe22fd6,0xb8c43b3b,0xb444bb77,0x3a6d36d7,0xbbb635c2,
0x3addb95f,0x2cb53be2,0xb81db9ed,0x3bfab179,0xbbea3564,0x2fd6bbff,0x30b23b88,0xbbf1a648,0x3bc32a48,0xb5053bce,0x33c6bbfe,0x3b993303,
0x3b64361f,0xbaf6367c,0x361fbb64,0x37e33b50,0xbb64b61f,0x3a0fb89b,0xb61f3b64,0xb93aba8a,0x3b64361f,0xb8ec39cb,0x361fbb64,0x3a4f3984,
0xbb64b61f,0x3732bac2,0xb61f3b64,0xbb25b848,0x30b2bb88,0x39843b25,0xbbeab564,0x39cbb732,0x33c63bfe,0xbbceb7e3,0x3bc3aa48,0xb3033af6,
0xb8c4bb3b,0x3b77acb5,0xba6d36d7,0xb5c2bbfa,0x3add395f,0xb89b38ec,0x381db9ed,0x3a8a3a4f,0xbbf6b4a5,0x3848b7e3,0x2e463ba8,0xbac2baf6,
0x3913b78b,0x367c3bfa,0xba2fbb0e,0x3b502cb5,0x2e463ba8,0xbbe2b8ec,0x3bf634a5,0xb1793a4f,0xba2fbb0e,0x3984b505,0xb913378b,0xb9cbbb99,
0x35643bc3,0xbb99bac2,0x3b8833c6,0xb5053848,0xbbfeb8c4,0x37e3b5c2,0xaa483a6d,0xbaf6bb77,0x36d7b81d,0x3a0f3be2,0xbb3bbadd,0x393ab179,
0x395f3bea,0xba4fa648,0x39edb0b2,0x38ec3bff,0x3aa7323e,0xacb5389b,0xb872bbd9,0x3bfa3a8a,0x38723bd9,0xbbf1b984,0x3aa7323e,0x2fd639cb,
0xbaa7b23e,0xb505bac2,0x38723bd9,0xbb99b848,0xb872bbd9,0x3af635c2,0xbaa7b23e,0xb7e3bb77,0xb9edbbea,0x3be23a4f,0xb95fb0b2,0xb179b8ec,
0x3564b3c6,0x39843b99,0xbb88bbc3,0x39cb3505,0x3bfe3a6d,0xb3033444,0xaa48b8c4,0x3bce3bb6,0x36d73add,0xbb77b93a,0x3b3b381d,0x35c23a0f,
0xb78bae46,0xb67cb93a,0x3b0e3bf6,0xbb50ba0f,0xbba8ba2f,0x3179afd6,0x34a53913,0xbbe2bbf1,0xbb0ebbf6,0x39843732,0xb78bae46,0xb9cbbb25,
0xb4a5b913,0x3bce3af6,0xbba8ba2f,0xb303b7e3,0x3bc33bfe,0xba4fb9cb,0x33c62a48,0x38ec3984,0x3a6d3b3b,0xbb25bac2,0x38c436d7,0x37323848,
0x381d395f,0xbbb6bb77,0x3add39ed,0x344435c2,0x30b23564,0xbbfabbe2,0x3bea3b88,0x2cb53179,0x3c003c00,0xafd6a648,0,0xbbf1bbff,
0x3c003c00,0xb505b303,0,0xbb99bbce,0x3c003c00,0xb7e3b67c,0,0xbaf6bb50,0x3c003c00,0xb93ab89b,0,0xba0fba8a,
0xbbc3bbfe,0x35c22cb5,0x33c62a48,0x3b773bfa,0xba6dbb3b,0x3a8a38ec,0x38c436d7,0x389b3a4f,0xb81db95f,0x3bff3b99,0x3add39ed,0x26483505,
0xb0b2b564,0x3ac23bb6,0x3bea3b88,0xb848b444,0x3b0e3bf6,0xb89bafd6,0xb78bae46,0xba8abbf1,0x34a53913,0xbbffbb25,0xbba8ba2f,0x2648b732,
0xb78bae46,0xb848baf6,0xbb0ebbf6,0x3ac237e3,0xbba8ba2f,0x367cacb5,0xb4a5b913,0x3b503bfa,0xb9edbbea,0x3a0f3179,0x395f30b2,0x393a3be2,
0x3564b3c6,0x3a4f3bff,0x3b883bc3,0xb8ec2648,0x3bfe3a6d,0xb7323303,0x2a4838c4,0xbb25bbce,0x36d73add,0xbbb6bb50,0xbb3bb81d,0x3444b67c,
0x38723bd9,0xbb25b303,0xbaa7b23e,0xb732bbce,0xbaa7b23e,0xb444bb50,0xb872bbd9,0x3bb6367c,0xb872bbd9,0x3bfa389b,0x3aa7323e,0x2cb53a8a,
0x3aa7323e,0xafd63984,0x38723bd9,0xbbf1b9cb,0xb564bbc3,0x3bce3444,0x3b8833c6,0x33033bb6,0x3bfe38c4,0xb5c2393a,0xaa483a6d,0xbb77ba0f,
0xb6d7381d,0xb89bbbf1,0xbb3bbadd,0x3a8aafd6,0xb95fbbea,0x3bff3732,0x39edb0b2,0x26483b25,0x2e463ba8,0xbbffb505,0xbbf6b4a5,0x2648bb99,
0xba2fbb0e,0x3ac2b444,0x3913b78b,0x38483bb6,0x3bf634a5,0xb67c3a0f,0x2e463ba8,0xbb50b93a,0xb913378b,0xb179bbf1,0xba2fbb0e,0x3be22fd6,
0x30b2bb88,0x3bb635c2,0x3bea3564,0xb4443b77,0x33c63bfe,0xbbfab179,0xbbc32a48,0x2cb5bbe2,0xb8c4bb3b,0x3bf1a648,0x3a6db6d7,0x2fd63bff,
0x3add395f,0xbb993303,0xb81d39ed,0xb505bbce,0xb61f3b64,0xbaf6b67c,0xbb64b61f,0x37e3bb50,0x361fbb64,0x3a0f389b,0x3b64361f,0xb93a3a8a,
0xb61f3b64,0xb8ecb9cb,0xbb64b61f,0x3a4fb984,0x361fbb64,0x37323ac2,0x3b64361f,0xbb253848,0x38c4bb3b,0x39cb3732,0x3a6d36d7,0xb9843b25,
0xbadd395f,0xb303baf6,0xb81db9ed,0x3bceb7e3,0x3beab564,0xb5c23bfa,0x30b23b88,0xbb77acb5,0xbbc3aa48,0x3a8aba4f,0x33c6bbfe,0x389b38ec,
0xba2f3b0e,0xb848b7e3,0xb913b78b,0x3ac2baf6,0x3bf6b4a5,0xb67c3bfa,0xae463ba8,0xbb502cb5,0xb913b78b,0x3be2b8ec,0x3a2fbb0e,0x31793a4f,
0xae463ba8,0xb984b505,0xbbf634a5,0x39cbbb99,0x3b3bbadd,0x35053848,0x36d7381d,0xbb993ac2,0xb9edb0b2,0x3af6bb77,0x395fbbea,0x37e335c2,
0xb5643bc3,0xb93ab179,0xbb8833c6,0x3a0fbbe2,0x3bfeb8c4,0xb8ec3bff,0x2a483a6d,0xba4f2648,0xbbd93aa7,0xacb5b89b,0xb23eb872,0x3bfaba8a,
0x323e3872,0xbbf13984,0xbbd93aa7,0x2fd6b9cb,0x3bd9baa7,0xb5053ac2,0x323e3872,0xbb993848,0xb23eb872,0x3af6b5c2,0x3bd9baa7,0xb7e33b77,
0x3bfeba6d,0xb17938ec,0xaa4838c4,0xbbe23a4f,0x36d7badd,0x39cbb505,0x3b3bb81d,0xb9843b99,0xb95f30b2,0x3bcebbb6,0x39edbbea,0x33033444,
0xbb883bc3,0x35c2ba0f,0xb564b3c6,0x3b77b93a,0xbba83a2f,0x367cb93a,0x34a5b913,0x3b50ba0f,0xbb0e3bf6,0xb179afd6,0xb78b2e46,0x3be2bbf1,
0xb4a53913,0xb9843732,0xbba83a2f,0x39cbbb25,0x378bae46,0xbbce3af6,0xbb0e3bf6,0x3303b7e3,0x3addb9ed,0xb8ec3984,0xb81d395f,0xba4f39cb,
0x3beabb88,0xb7323848,0xb0b23564,0xbb253ac2,0x3bc3bbfe,0xb44435c2,0x33c6aa48,0xbbb63b77,0x3a6dbb3b,0xacb53179,0x38c4b6d7,0xbbfa3be2,
0xb9a839a8,0x3a4fb9cb,0x39a8b9a8,0x38ecb984,0xb9a839a8,0x3b25bac2,0x39a8b9a8,0x3732b848,0xb9a839a8,0x3bb6bb77,0x39a8b9a8,0x3444b5c2,
0xb9a839a8,0x3bfabbe2,0x39a8b9a8,0x2cb5b179,0x381db95f,0xbb503a0f,0xbadd39ed,0xb67c393a,0x30b2b564,0xbbe23bf1,0xbbea3b88,0x31792fd6,
0xb3c62a48,0xb9cb3b25,0xbbc33bfe,0x3984b732,0xb8c436d7,0xb30337e3,0xba6d3b3b,0x3bcebaf6,0xb4a53913,0x3be2ba4f,0x3ba8ba2f,0x3179b8ec,
0x378bae46,0x3984bb99,0x3b0ebbf6,0xb9cb3505,0x3ba8ba2f,0xb303b444,0x34a5b913,0xbbce3bb6,0x3b0ebbf6,0xbb77393a,0xb78b2e46,0xb5c23a0f,
0x2a48b8c4,0xbbfa3a8a,0xbbfe3a6d,0x2cb5389b,0xbb3b381d,0xafd639cb,0xb6d73add,0x3bf1b984,0xb9ed3bea,0x3b99b848,0x395fb0b2,0x3505bac2,
0x356433c6,0x37e3bb77,0x3b88bbc3,0xbaf635c2,0x323e3872,0x3b99bac2,0x3bd9baa7,0xb505b848,0x3bd9baa7,0xb7e3b5c2,0xb23eb872,0xbaf63b77,
0xb23eb872,0xba0f3be2,0xbbd93aa7,0x393a3179,0xbbd93aa7,0x3a4fa648,0x323e3872,0x38ecbbff,0xb6d7b81d,0xbac23af6,0xbb3b3add,0x384837e3,
0xb95f3bea,0x3b50acb5,0x39ed30b2,0x367cbbfa,0x3b88b3c6,0xb179ba4f,0x3564bbc3,0xbbe238ec,0xaa48ba6d,0xb9cb3b99,0xbbfe38c4,0x39843505,
0x3913378b,0x3984bb25,0x3a2fbb0e,0xb9cbb732,0x2e46bba8,0xbbce37e3,0xbbf634a5,0x33033af6,0xba2f3b0e,0x3b772cb5,0x3913378b,0x35c2bbfa,
0x3bf6b4a5,0xb89bb8ec,0x2e46bba8,0xba8a3a4f,0xba6db6d7,0xb7e33b50,0xb8c43b3b,0x3af6367c,0x381d39ed,0x393aba8a,0x3addb95f,0xba0fb89b,
0xb0b2bb88,0xba4f3984,0xbbea3564,0x38ec39cb,0xb3c63bfe,0x3b25b848,0x3bc32a48,0xb732bac2,0x3b64361f,0x3444bb77,0x361fbb64,0xbbb6b5c2,
0xbb64b61f,0xacb53be2,0xb61f3b64,0x3bfa3179,0x3b64361f,0xafd6bbff,0x361fbb64,0xbbf12648,0xbb64b61f,0x35053bce,0xb61f3b64,0x3b99b303,
0xbbeab564,0xa6483b99,0xb0b23b88,0x3bff3505,0x3bc3aa48,0xb848bbb6,0xb3c6bbfe,0xbac23444,0xba6d36d7,0x3b50393a,0x38c43b3b,0x367cba0f,
0x381db9ed,0xbbe2afd6,0xbaddb95f,0x31793bf1,0x3bf634a5,0xb303bbb6,0xae46bba8,0xbbceb444,0xb913378b,0x3b773a0f,0x3a2f3b0e,0x35c2b93a,
0xae46bba8,0xba8a2fd6,0xbbf6b4a5,0x389b3bf1,0x3a2f3b0e,0xa648bb25,0x3913b78b,0xbbffb732,0xbb88b3c6,0x37323bce,0x35643bc3,0x3b253303,
0x2a48ba6d,0xbbb6b67c,0xbbfeb8c4,0x34443b50,0x3b3b3add,0xacb5ba8a,0x36d7b81d,0xbbfab89b,0xb9ed30b2,0x3bf139cb,0x395f3bea,0x2fd6b984,
0x3aa7323e,0xb93abbe2,0xb872bbd9,0xba0fb179,0x38723bd9,0x38eca648,0x3aa7323e,0xba4fbbff,0xbaa7b23e,0x3b253bce,0x38723bd9,0x3732b303,
0xb872bbd9,0xb444367c,0xbaa7b23e,0x3bb63b50,0xb95fb0b2,0x3a8a3bf1,0x39ed3bea,0x389b2fd6,0xbb88bbc3,0xa6483732,0xb56433c6,0x3bff3b25,
0xaa48b8c4,0xbac2b7e3,0xbbfeba6d,0x38483af6,0x3b3b381d,0xbb50bbfa,0xb6d7badd,0xb67c2cb5,0x378b2e46,0xbb77bbfa,0xbb0ebbf6,0xb5c2acb5,
0x3ba83a2f,0xb89bba4f,0xb4a5b913,0xba8ab8ec,0x3b0e3bf6,0xa648b505,0x378b2e46,0xbbffbb99,0x34a53913,0x38483444,0x3ba83a2f,0xbac2bbb6,
0xb3c6aa48,0x3bf13bff,0x3bc33bfe,0x2fd62648,0xb8c4b6d7,0x3b993bce,0x3a6d3b3b,0x35053303,0xbaddb9ed,0x3af63b50,0x381d395f,0x37e3367c,
0xbbeabb88,0x3a0f3a8a,0x30b23564,0x393a389b,0x3c003c00,0x2fd62648,0,0x3bf13bff,0x3c003c00,0x35053303,0,0x3b993bce,
0x3c003c00,0x37e3367c,0,0x3af63b50,0x3c003c00,0x393a389b,0,0x3a0f3a8a,0xbbc3bbfe,0xb5c2acb5,0x33c62a48,0xbb77bbfa,
0xba6dbb3b,0xba8ab8ec,0x38c436d7,0xb89bba4f,0xb81db95f,0xbbffbb99,0x3add39ed,0xa648b505,0xb0b2b564,0xbac2bbb6,0x3bea3b88,0x38483444,
0x3b0e3bf6,0x389b2fd6,0xb78bae46,0x3a8a3bf1,0x34a53913,0x3bff3b25,0xbba8ba2f,0xa6483732,0xb78bae46,0x38483af6,0xbb0ebbf6,0xbac2b7e3,
0xbba8ba2f,0xb67c2cb5,0xb4a5b913,0xbb50bbfa,0xb9edbbea,0xba0fb179,0x395f30b2,0xb93abbe2,0x3564b3c6,0xba4fbbff,0x3b883bc3,0x38eca648,
0x3bfe3a6d,0x3732b303,0x2a4838c4,0x3b253bce,0x36d73add,0x3bb63b50,0xbb3bb81d,0xb444367c,0x38723bd9,0x3b253303,0xbaa7b23e,0x37323bce,
0xbaa7b23e,0x34443b50,0xb872bbd9,0xbbb6b67c,0xb872bbd9,0xbbfab89b,0x3aa7323e,0xacb5ba8a,0x3aa7323e,0x2fd6b984,0x38723bd9,0x3bf139cb,
0xb564bbc3,0xbbceb444,0x3b8833c6,0xb303bbb6,0x3bfe38c4,0x35c2b93a,0xaa483a6d,0x3b773a0f,0xb6d7381d,0x389b3bf1,0xbb3bbadd,0xba8a2fd6,
0xb95fbbea,0xbbffb732,0x39edb0b2,0xa648bb25,0x2e463ba8,0x3bff3505,0xbbf6b4a5,0xa6483b99,0xba2fbb0e,0xbac23444,0x3913b78b,0xb848bbb6,
0x3bf634a5,0x367cba0f,0x2e463ba8,0x3b50393a,0xb913378b,0x31793bf1,0xba2fbb0e,0xbbe2afd6,0x30b2bb88,0xbbb6b5c2,0x3bea3564,0x3444bb77,
0x33c63bfe,0x3bfa3179,0xbbc32a48,0xacb53be2,0xb8c4bb3b,0xbbf12648,0x3a6db6d7,0xafd6bbff,0x3add395f,0x3b99b303,0xb81d39ed,0x35053bce,
0xb61f3b64,0x3af6367c,0xbb64b61f,0xb7e33b50,0x361fbb64,0xba0fb89b,0x3b64361f,0x393aba8a,0xb61f3b64,0x38ec39cb,0xbb64b61f,0xba4f3984,
0x361fbb64,0xb732bac2,0x3b64361f,0x3b25b848,0x38c4bb3b,0xb9cbb732,0x3a6d36d7,0x3984bb25,0xbadd395f,0x33033af6,0xb81db9ed,0xbbce37e3,
0x3beab564,0x35c2bbfa,0x30b23b88,0x3b772cb5,0xbbc3aa48,0xba8a3a4f,0x33c6bbfe,0xb89bb8ec,0xba2f3b0e,0x384837e3,0xb913b78b,0xbac23af6,
0x3bf6b4a5,0x367cbbfa,0xae463ba8,0x3b50acb5,0xb913b78b,0xbbe238ec,0x3a2fbb0e,0xb179ba4f,0xae463ba8,0x39843505,0xbbf634a5,0xb9cb3b99,
0x3b3bbadd,0xb505b848,0x36d7381d,0x3b99bac2,0xb9edb0b2,0xbaf63b77,0x395fbbea,0xb7e3b5c2,0xb5643bc3,0x393a3179,0xbb8833c6,0xba0f3be2,
0x3bfeb8c4,0x38ecbbff,0x2a483a6d,0x3a4fa648,0xbbd93aa7,0x2cb5389b,0xb23eb872,0xbbfa3a8a,0x323e3872,0x3bf1b984,0xbbd93aa7,0xafd639cb,
0x3bd9baa7,0x3505bac2,0x323e3872,0x3b99b848,0xb23eb872,0xbaf635c2,0x3bd9baa7,0x37e3bb77,0x3bfeba6d,0x3179b8ec,0xaa4838c4,0x3be2ba4f,
0x36d7badd,0xb9cb3505,0x3b3bb81d,0x3984bb99,0xb95f30b2,0xbbce3bb6,0x39edbbea,0xb303b444,0xbb883bc3,0xb5c23a0f,0xb564b3c6,0xbb77393a,
0xbba83a2f,0xb67c393a,0x34a5b913,0xbb503a0f,0xbb0e3bf6,0x31792fd6,0xb78b2e46,0xbbe23bf1,0xb4a53913,0x3984b732,0xbba83a2f,0xb9cb3b25,
0x378bae46,0x3bcebaf6,0xbb0e3bf6,0xb30337e3,0x3addb9ed,0x38ecb984,0xb81d395f,0x3a4fb9cb,0x3beabb88,0x3732b848,0xb0b23564,0x3b25bac2,
0x3bc3bbfe,0x3444b5c2,0x33c6aa48,0x3bb6bb77,0x3a6dbb3b,0x2cb5b179,0x38c4b6d7,0x3bfabbe2,0xb9a839a8,0xba4f39cb,0x39a8b9a8,0xb8ec3984,
0xb9a839a8,0xbb253ac2,0x39a8b9a8,0xb7323848,0xb9a839a8,0xbbb63b77,0x39a8b9a8,0xb44435c2,0xb9a839a8,0xbbfa3be2,0x39a8b9a8,0xacb53179,
0x381db95f,0x3b50ba0f,0xbadd39ed,0x367cb93a,0x30b2b564,0x3be2bbf1,0xbbea3b88,0xb179afd6,0xb3c62a48,0x39cbbb25,0xbbc33bfe,0xb9843732,
0xb8c436d7,0x3303b7e3,0xba6d3b3b,0xbbce3af6,0xb4a53913,0xbbe23a4f,0x3ba8ba2f,0xb17938ec,0x378bae46,0xb9843b99,0x3b0ebbf6,0x39cbb505,
0x3ba8ba2f,0x33033444,0x34a5b913,0x3bcebbb6,0x3b0ebbf6,0x3b77b93a,0xb78b2e46,0x35c2ba0f,0x2a48b8c4,0x3bfaba8a,0xbbfe3a6d,0xacb5b89b,
0xbb3b381d,0x2fd6b9cb,0xb6d73add,0xbbf13984,0xb9ed3bea,0xbb993848,0x395fb0b2,0xb5053ac2,0x356433c6,0xb7e33b77,0x3b88bbc3,0x3af6b5c2,
0x323e3872,0xbb993ac2,0x3bd9baa7,0x35053848,0x3bd9baa7,0x37e335c2,0xb23eb872,0x3af6bb77,0xb23eb872,0x3a0fbbe2,0xbbd93aa7,0xb93ab179,
0xbbd93aa7,0xba4f2648,0x323e3872,0xb8ec3bff,0xb6d7b81d,0x3ac2baf6,0xbb3b3add,0xb848b7e3,0xb95f3bea,0xbb502cb5,0x39ed30b2,0xb67c3bfa,
0x3b88b3c6,0x31793a4f,0x3564bbc3,0x3be2b8ec,0xaa48ba6d,0x39cbbb99,0xbbfe38c4,0xb984b505,0x3913378b,0xb9843b25,0x3a2fbb0e,0x39cb3732,
0x2e46bba8,0x3bceb7e3,0xbbf634a5,0xb303baf6,0xba2f3b0e,0xbb77acb5,0x3913378b,0xb5c23bfa,0x3bf6b4a5,0x389b38ec,0x2e46bba8,0x3a8aba4f,
0xba6db6d7,0x37e3bb50,0xb8c43b3b,0xbaf6b67c,0x381d39ed,0xb93a3a8a,0x3addb95f,0x3a0f389b,0xb0b2bb88,0x3a4fb984,0xbbea3564,0xb8ecb9cb,
0xb3c63bfe,0xbb253848,0x3bc32a48,0x37323ac2,0x3b64361f,0xb4443b77,0x361fbb64,0x3bb635c2,0xbb64b61f,0x2cb5bbe2,0xb61f3b64,0xbbfab179,
0x3b64361f,0x2fd63bff,0x361fbb64,0x3bf1a648,0xbb64b61f,0xb505bbce,0xb61f3b64,0xbb993303,0xbbeab564,0x2648bb99,0xb0b23b88,0xbbffb505,
0x3bc3aa48,0x38483bb6,0xb3c6bbfe,0x3ac2b444,0xba6d36d7,0xbb50b93a,0x38c43b3b,0xb67c3a0f,0x381db9ed,0x3be22fd6,0xbaddb95f,0xb179bbf1,
0x3bf634a5,0x33033bb6,0xae46bba8,0x3bce3444,0xb913378b,0xbb77ba0f,0x3a2f3b0e,0xb5c2393a,0xae46bba8,0x3a8aafd6,0xbbf6b4a5,0xb89bbbf1,
0x3a2f3b0e,0x26483b25,0x3913b78b,0x3bff3732,0xbb88b3c6,0xb732bbce,0x35643bc3,0xbb25b303,0x2a48ba6d,0x3bb6367c,0xbbfeb8c4,0xb444bb50,
0x3b3b3add,0x2cb53a8a,0x36d7b81d,0x3bfa389b,0xb9ed30b2,0xbbf1b9cb,0x395f3bea,0xafd63984,0x3aa7323e,0x393a3be2,0xb872bbd9,0x3a0f3179,
0x38723bd9,0xb8ec2648,0x3aa7323e,0x3a4f3bff,0xbaa7b23e,0xbb25bbce,0x38723bd9,0xb7323303,0xb872bbd9,0x3444b67c,0xbaa7b23e,0xbbb6bb50,
0xb95fb0b2,0xba8abbf1,0x39ed3bea,0xb89bafd6,0xbb88bbc3,0x2648b732,0xb56433c6,0xbbffbb25,0xaa48b8c4,0x3ac237e3,0xbbfeba6d,0xb848baf6,
0x3b3b381d,0x3b503bfa,0xb6d7badd,0x367cacb5,0x378b2e46,0x3b773bfa,0xbb0ebbf6,0x35c22cb5,0x3ba83a2f,0x389b3a4f,0xb4a5b913,0x3a8a38ec,
0x3b0e3bf6,0x26483505,0x378b2e46,0x3bff3b99,0x34a53913,0xb848b444,0x3ba83a2f,0x3ac23bb6,0xb3c6aa48,0xbbf1bbff,0x3bc33bfe,0xafd6a648,
0xb8c4b6d7,0xbb99bbce,0x3a6d3b3b,0xb505b303,0xbaddb9ed,0xbaf6bb50,0x381d395f,0xb7e3b67c,0xbbeabb88,0xba0fba8a,0x30b23564,0xb93ab89b,
0x3c003c00,0xba4fb9cb,0,0xb8ecb984,0x3c003c00,0xbb25bac2,0,0xb732b848,0x3c003c00,0xbbb6bb77,0,0xb444b5c2,
0x3c003c00,0xbbfabbe2,0,0xacb5b179,0x33c62a48,0x367c393a,0x3bc33bfe,0xbb50ba0f,0x38c436d7,0xb1792fd6,0x3a6d3b3b,0xbbe2bbf1,
0x3add39ed,0xb984b732,0x381d395f,0xb9cbbb25,0x3bea3b88,0xbbcebaf6,0x30b23564,0xb303b7e3,0xbb0ebbf6,0x3be23a4f,0x378b2e46,0x317938ec,
0xb4a5b913,0x39843b99,0x3ba83a2f,0xb9cbb505,0x378b2e46,0xb3033444,0x3b0e3bf6,0xbbcebbb6,0x3ba83a2f,0xbb77b93a,0x34a53913,0xb5c2ba0f,
0xb95fb0b2,0x2cb5b89b,0xb9edbbea,0x3bfa3a8a,0xbb88bbc3,0x3bf13984,0x3564b3c6,0x2fd639cb,0xaa48b8c4,0x35053ac2,0x3bfe3a6d,0xbb99b848,
0x3b3b381d,0xbaf6b5c2,0x36d73add,0xb7e3bb77,0x38723bd9,0xbb99bac2,0xbaa7b23e,0x3505b848,0xbaa7b23e,0x37e3b5c2,0xb872bbd9,0x3af63b77,
0xb872bbd9,0x3a0f3be2,0x3aa7323e,0xb93a3179,0x3aa7323e,0xba4fa648,0x38723bd9,0xb8ecbbff,0x3b8833c6,0xb84837e3,0x35643bc3,0xbac2baf6,
0xaa483a6d,0xb67cbbfa,0xbbfeb8c4,0x3b502cb5,0xbb3bbadd,0x3be238ec,0x36d7b81d,0xb1793a4f,0x39edb0b2,0xb9843505,0x395f3bea,0xb9cbbb99,
0xae46bba8,0x39843b25,0x3bf634a5,0xb9cb3732,0x3a2f3b0e,0xbbceb7e3,0xb913378b,0x3303baf6,0xbbf6b4a5,0x3b77acb5,0xae46bba8,0x35c23bfa,
0x3913b78b,0xb89b38ec,0x3a2f3b0e,0xba8aba4f,0xbbeab564,0x3af6b67c,0x30b2bb88,0x37e33b50,0x3bc3aa48,0xba0f389b,0x33c63bfe,0xb93aba8a,
0xba6d36d7,0x38ecb9cb,0xb8c4bb3b,0x3a4f3984,0x381db9ed,0xb7323ac2,0x3add395f,0xbb25b848,0xb61f3b64,0xb444bb77,0xbb64b61f,0x3bb6b5c2,
0x361fbb64,0x2cb53be2,0x3b64361f,0xbbfa3179,0xb61f3b64,0x2fd6bbff,0xbb64b61f,0x3bf12648,0x361fbb64,0xb5053bce,0x3b64361f,0xbb99b303,
0x3a6d36d7,0xbbff3505,0xb8c43b3b,0xa648bb99,0xb81db9ed,0x3ac23444,0x3addb95f,0xb8483bb6,0x30b23b88,0xb67cba0f,0xbbea3564,0x3b50b93a,
0x33c6bbfe,0xb1793bf1,0x3bc32a48,0xbbe22fd6,0x3a2fbb0e,0xb3033bb6,0x3913378b,0xbbce3444,0xbbf634a5,0x3b77ba0f,0x2e46bba8,0x35c2393a,
0x3913378b,0xba8aafd6,0xba2f3b0e,0x389bbbf1,0x2e46bba8,0xa6483b25,0x3bf6b4a5,0xbbff3732,0xb6d7b81d,0x3b25b303,0x3b3bbadd,0xb7323bce,
0xb95f3bea,0x3444bb50,0xb9edb0b2,0x3bb6b67c,0x3b88b3c6,0xbbfa389b,0xb5643bc3,0x2cb5ba8a,0xaa48ba6d,0x2fd63984,0x3bfeb8c4,0xbbf139cb,
0xbbd93aa7,0x393abbe2,0xb23eb872,0x3a0fb179,0x323e3872,0xb8eca648,0xbbd93aa7,0x3a4fbbff,0x3bd9baa7,0xbb253bce,0x323e3872,0xb732b303,
0xb23eb872,0x3444367c,0x3bd9baa7,0xbbb63b50,0xaa4838c4,0xb89b2fd6,0xbbfe3a6d,0x3a8abbf1,0x3b3bb81d,0xbbff3b25,0xb6d73add,0xa648b732,
0x39edbbea,0xb8483af6,0x395fb0b2,0xbac237e3,0xb564b3c6,0x367c2cb5,0x3b88bbc3,0xbb503bfa,0x3ba8ba2f,0xbb773bfa,0xb4a53913,0xb5c22cb5,
0x3b0ebbf6,0xb89b3a4f,0x378bae46,0xba8a38ec,0x34a5b913,0xa6483505,0x3ba8ba2f,0xbbff3b99,0xb78b2e46,0x3848b444,0x3b0ebbf6,0xbac23bb6,
0x381db95f,0x2fd6a648,0x3addb9ed,0xbbf13bff,0x30b2b564,0x3505b303,0x3beabb88,0xbb993bce,0xb3c62a48,0x37e3b67c,0x3bc3bbfe,0xbaf63b50,
0xb8c436d7,0x393ab89b,0x3a6dbb3b,0xba0f3a8a,0xb9a839a8,0x3bf1bbff,0x39a8b9a8,0xafd62648,0xb9a839a8,0x3b99bbce,0x39a8b9a8,0xb5053303,
0xb9a839a8,0x3af6bb50,0x39a8b9a8,0xb7e3367c,0xb9a839a8,0x3a0fba8a,0x39a8b9a8,0xb93a389b,0xbadd39ed,0x35c2acb5,0xb81d395f,0x3b77bbfa,
0xbbea3b88,0x3a8ab8ec,0xb0b23564,0x389bba4f,0xbbc33bfe,0x3bffbb99,0x33c6aa48,0x2648b505,0xba6d3b3b,0x3ac2bbb6,0x38c4b6d7,0xb8483444,
0x34a5b913,0xba8a3bf1,0xbba83a2f,0x389bafd6,0xb78b2e46,0x26483732,0xbb0e3bf6,0x3bffbb25,0xbba83a2f,0x3ac2b7e3,0xb4a53913,0x3848baf6,
0xbb0e3bf6,0x3b50bbfa,0x378bae46,0xb67cacb5,0x3bfeba6d,0xba0f3179,0x2a48b8c4,0xb93a3be2,0x36d7badd,0xba4f3bff,0xbb3b381d,0x38ec2648,
0xb95f30b2,0x37323303,0xb9ed3bea,0x3b25bbce,0xbb883bc3,0x3bb6bb50,0x356433c6,0xb444b67c,0x323e3872,0x3732bbce,0x3bd9baa7,0xbb253303,
0x3bd9baa7,0xbbb6367c,0xb23eb872,0xb4443b50,0xb23eb872,0xacb53a8a,0xbbd93aa7,0x3bfab89b,0xbbd93aa7,0x3bf1b9cb,0x323e3872,0xafd6b984,
0xbb3b3add,0x3bceb444,0x36d7381d,0x3303bbb6,0x39ed30b2,0xb5c2b93a,0x395fbbea,0xbb773a0f,0x3564bbc3,0xb89b3bf1,0xbb8833c6,0x3a8a2fd6,
0xbbfe38c4,0x3bffb732,0x2a483a6d,0x2648bb25,0xb913b78b,0x26483b99,0xba2f3b0e,0x3bffb505,0xae463ba8,0x3848bbb6,0x3bf6b4a5,0xbac2b444,
0x3a2fbb0e,0xbb50393a,0xb913b78b,0x367c3a0f,0xbbf634a5,0x3be2afd6,0xae463ba8,0x3179bbf1,0x38c4bb3b,0xbbb635c2,0xba6db6d7,0x34443b77,
0xbadd395f,0x3bfab179,0x381d39ed,0xacb5bbe2,0x3beab564,0xbbf1a648,0xb0b2bb88,0xafd63bff,0xbbc3aa48,0x3b993303,0xb3c63bfe,0x3505bbce,
0x3b64361f,0xb7e3bb50,0x361fbb64,0xbaf6367c,0xbb64b61f,0x393a3a8a,0xb61f3b64,0x3a0fb89b,0x3b64361f,0xba4fb984,0x361fbb64,0xb8ec39cb,
0xbb64b61f,0x3b253848,0xb61f3b64,0x3732bac2,0xb0b23b88,0x39cbb732,0x3bea3564,0xb984bb25,0xb3c6bbfe,0xb3033af6,0xbbc32a48,0x3bce37e3,
0x38c43b3b,0xb5c2bbfa,0x3a6db6d7,0xbb772cb5,0xbaddb95f,0x3a8a3a4f,0xb81d39ed,0x389bb8ec,0xbbf6b4a5,0x3ac23af6,0x2e463ba8,0x3848b7e3,
0x3913b78b,0xbb50acb5,0xba2fbb0e,0x367c3bfa,0x2e463ba8,0x3179ba4f,0x3bf634a5,0xbbe2b8ec,0xba2fbb0e,0x39cb3b99,0xb913378b,0x3984b505,
0xb564bbc3,0xb5053848,0xbb88b3c6,0x3b993ac2,0x3bfe38c4,0xbaf6bb77,0x2a48ba6d,0xb7e335c2,0xb6d7381d,0x393ab179,0x3b3b3add,0xba0fbbe2,
0xb95fbbea,0x38ec3bff,0xb9ed30b2,0x3a4f2648,0x3aa7323e,0xbbfaba8a,0xb872bbd9,0xacb5389b,0x38723bd9,0xafd6b9cb,0x3aa7323e,0xbbf1b984,
0xbaa7b23e,0x3b993848,0x38723bd9,0xb505bac2,0xb872bbd9,0x37e33b77,0xbaa7b23e,0x3af635c2,0x39ed3bea,0xb179b8ec,0x395f30b2,0xbbe2ba4f,
0xb56433c6,0x39cb3505,0x3b883bc3,0xb984bb99,0xbbfeba6d,0x3bce3bb6,0x2a4838c4,0x3303b444,0xb6d7badd,0x35c23a0f,0xbb3bb81d,0x3b77393a,
0xb78bae46,0x3b503a0f,0x3b0e3bf6,0xb67cb93a,0xbba8ba2f,0x3be23bf1,0x34a53913,0x3179afd6,0xbb0ebbf6,0x39cb3b25,0xb78bae46,0x39843732,
0xb4a5b913,0x330337e3,0xbba8ba2f,0x3bce3af6,0xbbc3bbfe,0x38ec3984,0xb3c6aa48,0x3a4f39cb,0xba6dbb3b,0x37323848,0xb8c4b6d7,0x3b253ac2,
0xb81db95f,0x344435c2,0xbaddb9ed,0x3bb63b77,0xb0b2b564,0x2cb53179,0xbbeabb88,0x3bfa3be2,0x3c003c00,0x3a4f39cb,0,0x38ec3984,
0x3c003c00,0x3b253ac2,0,0x37323848,0x3c003c00,0x3bb63b77,0,0x344435c2,0x3c003c00,0x3bfa3be2,0,0x2cb53179,
0x33c62a48,0xb67cb93a,0x3bc33bfe,0x3b503a0f,0x38c436d7,0x3179afd6,0x3a6d3b3b,0x3be23bf1,0x3add39ed,0x39843732,0x381d395f,0x39cb3b25,
0x3bea3b88,0x3bce3af6,0x30b23564,0x330337e3,0xbb0ebbf6,0xbbe2ba4f,0x378b2e46,0xb179b8ec,0xb4a5b913,0xb984bb99,0x3ba83a2f,0x39cb3505,
0x378b2e46,0x3303b444,0x3b0e3bf6,0x3bce3bb6,0x3ba83a2f,0x3b77393a,0x34a53913,0x35c23a0f,0xb95fb0b2,0xacb5389b,0xb9edbbea,0xbbfaba8a,
0xbb88bbc3,0xbbf1b984,0x3564b3c6,0xafd6b9cb,0xaa48b8c4,0xb505bac2,0x3bfe3a6d,0x3b993848,0x3b3b381d,0x3af635c2,0x36d73add,0x37e33b77,
0x38723bd9,0x3b993ac2,0xbaa7b23e,0xb5053848,0xbaa7b23e,0xb7e335c2,0xb872bbd9,0xbaf6bb77,0xb872bbd9,0xba0fbbe2,0x3aa7323e,0x393ab179,
0x3aa7323e,0x3a4f2648,0x38723bd9,0x38ec3bff,0x3b8833c6,0x3848b7e3,0x35643bc3,0x3ac23af6,0xaa483a6d,0x367c3bfa,0xbbfeb8c4,0xbb50acb5,
0xbb3bbadd,0xbbe2b8ec,0x36d7b81d,0x3179ba4f,0x39edb0b2,0x3984b505,0x395f3bea,0x39cb3b99,0xae46bba8,0xb984bb25,0x3bf634a5,0x39cbb732,
0x3a2f3b0e,0x3bce37e3,0xb913378b,0xb3033af6,0xbbf6b4a5,0xbb772cb5,0xae46bba8,0xb5c2bbfa,0x3913b78b,0x389bb8ec,0x3a2f3b0e,0x3a8a3a4f,
0xbbeab564,0xbaf6367c,0x30b2bb88,0xb7e3bb50,0x3bc3aa48,0x3a0fb89b,0x33c63bfe,0x393a3a8a,0xba6d36d7,0xb8ec39cb,0xb8c4bb3b,0xba4fb984,
0x381db9ed,0x3732bac2,0x3add395f,0x3b253848,0xb61f3b64,0x34443b77,0xbb64b61f,0xbbb635c2,0x361fbb64,0xacb5bbe2,0x3b64361f,0x3bfab179,
0xb61f3b64,0xafd63bff,0xbb64b61f,0xbbf1a648,0x361fbb64,0x3505bbce,0x3b64361f,0x3b993303,0x3a6d36d7,0x3bffb505,0xb8c43b3b,0x26483b99,
0xb81db9ed,0xbac2b444,0x3addb95f,0x3848bbb6,0x30b23b88,0x367c3a0f,0xbbea3564,0xbb50393a,0x33c6bbfe,0x3179bbf1,0x3bc32a48,0x3be2afd6,
0x3a2fbb0e,0x3303bbb6,0x3913378b,0x3bceb444,0xbbf634a5,0xbb773a0f,0x2e46bba8,0xb5c2b93a,0x3913378b,0x3a8a2fd6,0xba2f3b0e,0xb89b3bf1,
0x2e46bba8,0x2648bb25,0x3bf6b4a5,0x3bffb732,0xb6d7b81d,0xbb253303,0x3b3bbadd,0x3732bbce,0xb95f3bea,0xb4443b50,0xb9edb0b2,0xbbb6367c,
0x3b88b3c6,0x3bfab89b,0xb5643bc3,0xacb53a8a,0xaa48ba6d,0xafd6b984,0x3bfeb8c4,0x3bf1b9cb,0xbbd93aa7,0xb93a3be2,0xb23eb872,0xba0f3179,
0x323e3872,0x38ec2648,0xbbd93aa7,0xba4f3bff,0x3bd9baa7,0x3b25bbce,0x323e3872,0x37323303,0xb23eb872,0xb444b67c,0x3bd9baa7,0x3bb6bb50,
0xaa4838c4,0x389bafd6,0xbbfe3a6d,0xba8a3bf1,0x3b3bb81d,0x3bffbb25,0xb6d73add,0x26483732,0x39edbbea,0x3848baf6,0x395fb0b2,0x3ac2b7e3,
0xb564b3c6,0xb67cacb5,0x3b88bbc3,0x3b50bbfa,0x3ba8ba2f,0x3b77bbfa,0xb4a53913,0x35c2acb5,0x3b0ebbf6,0x389bba4f,0x378bae46,0x3a8ab8ec,
0x34a5b913,0x2648b505,0x3ba8ba2f,0x3bffbb99,0xb78b2e46,0xb8483444,0x3b0ebbf6,0x3ac2bbb6,0x381db95f,0xafd62648,0x3addb9ed,0x3bf1bbff,
0x30b2b564,0xb5053303,0x3beabb88,0x3b99bbce,0xb3c62a48,0xb7e3367c,0x3bc3bbfe,0x3af6bb50,0xb8c436d7,0xb93a389b,0x3a6dbb3b,0x3a0fba8a,
0xb9a839a8,0xbbf13bff,0x39a8b9a8,0x2fd6a648,0xb9a839a8,0xbb993bce,0x39a8b9a8,0x3505b303,0xb9a839a8,0xbaf63b50,0x39a8b9a8,0x37e3b67c,
0xb9a839a8,0xba0f3a8a,0x39a8b9a8,0x393ab89b,0xbadd39ed,0xb5c22cb5,0xb81d395f,0xbb773bfa,0xbbea3b88,0xba8a38ec,0xb0b23564,0xb89b3a4f,
0xbbc33bfe,0xbbff3b99,0x33c6aa48,0xa6483505,0xba6d3b3b,0xbac23bb6,0x38c4b6d7,0x3848b444,0x34a5b913,0x3a8abbf1,0xbba83a2f,0xb89b2fd6,
0xb78b2e46,0xa648b732,0xbb0e3bf6,0xbbff3b25,0xbba83a2f,0xbac237e3,0xb4a53913,0xb8483af6,0xbb0e3bf6,0xbb503bfa,0x378bae46,0x367c2cb5,
0x3bfeba6d,0x3a0fb179,0x2a48b8c4,0x393abbe2,0x36d7badd,0x3a4fbbff,0xbb3b381d,0xb8eca648,0xb95f30b2,0xb732b303,0xb9ed3bea,0xbb253bce,
0xbb883bc3,0xbbb63b50,0x356433c6,0x3444367c,0x323e3872,0xb7323bce,0x3bd9baa7,0x3b25b303,0x3bd9baa7,0x3bb6b67c,0xb23eb872,0x3444bb50,
0xb23eb872,0x2cb5ba8a,0xbbd93aa7,0xbbfa389b,0xbbd93aa7,0xbbf139cb,0x323e3872,0x2fd63984,0xbb3b3add,0xbbce3444,0x36d7381d,0xb3033bb6,
0x39ed30b2,0x35c2393a,0x395fbbea,0x3b77ba0f,0x3564bbc3,0x389bbbf1,0xbb8833c6,0xba8aafd6,0xbbfe38c4,0xbbff3732,0x2a483a6d,0xa6483b25,
0xb913b78b,0xa648bb99,0xba2f3b0e,0xbbff3505,0xae463ba8,0xb8483bb6,0x3bf6b4a5,0x3ac23444,0x3a2fbb0e,0x3b50b93a,0xb913b78b,0xb67cba0f,
0xbbf634a5,0xbbe22fd6,0xae463ba8,0xb1793bf1,0x38c4bb3b,0x3bb6b5c2,0xba6db6d7,0xb444bb77,0xbadd395f,0xbbfa3179,0x381d39ed,0x2cb53be2,
0x3beab564,0x3bf12648,0xb0b2bb88,0x2fd6bbff,0xbbc3aa48,0xbb99b303,0xb3c63bfe,0xb5053bce,0x3b64361f,0x37e33b50,0x361fbb64,0x3af6b67c,
0xbb64b61f,0xb93aba8a,0xb61f3b64,0xba0f389b,0x3b64361f,0x3a4f3984,0x361fbb64,0x38ecb9cb,0xbb64b61f,0xbb25b848,0xb61f3b64,0xb7323ac2,
0xb0b23b88,0xb9cb3732,0x3bea3564,0x39843b25,0xb3c6bbfe,0x3303baf6,0xbbc32a48,0xbbceb7e3,0x38c43b3b,0x35c23bfa,0x3a6db6d7,0x3b77acb5,
0xbaddb95f,0xba8aba4f,0xb81d39ed,0xb89b38ec,0xbbf6b4a5,0xbac2baf6,0x2e463ba8,0xb84837e3,0x3913b78b,0x3b502cb5,0xba2fbb0e,0xb67cbbfa,
0x2e463ba8,0xb1793a4f,0x3bf634a5,0x3be238ec,0xba2fbb0e,0xb9cbbb99,0xb913378b,0xb9843505,0xb564bbc3,0x3505b848,0xbb88b3c6,0xbb99bac2,
0x3bfe38c4,0x3af63b77,0x2a48ba6d,0x37e3b5c2,0xb6d7381d,0xb93a3179,0x3b3b3add,0x3a0f3be2,0xb95fbbea,0xb8ecbbff,0xb9ed30b2,0xba4fa648,
0x3aa7323e,0x3bfa3a8a,0xb872bbd9,0x2cb5b89b,0x38723bd9,0x2fd639cb,0x3aa7323e,0x3bf13984,0xbaa7b23e,0xbb99b848,0x38723bd9,0x35053ac2,
0xb872bbd9,0xb7e3bb77,0xbaa7b23e,0xbaf6b5c2,0x39ed3bea,0x317938ec,0x395f30b2,0x3be23a4f,0xb56433c6,0xb9cbb505,0x3b883bc3,0x39843b99,
0xbbfeba6d,0xbbcebbb6,0x2a4838c4,0xb3033444,0xb6d7badd,0xb5c2ba0f,0xbb3bb81d,0xbb77b93a,0xb78bae46,0xbb50ba0f,0x3b0e3bf6,0x367c393a,
0xbba8ba2f,0xbbe2bbf1,0x34a53913,0xb1792fd6,0xbb0ebbf6,0xb9cbbb25,0xb78bae46,0xb984b732,0xb4a5b913,0xb303b7e3,0xbba8ba2f,0xbbcebaf6,
0xbbc3bbfe,0xb8ecb984,0xb3c6aa48,0xba4fb9cb,0xba6dbb3b,0xb732b848,0xb8c4b6d7,0xbb25bac2,0xb81db95f,0xb444b5c2,0xbaddb9ed,0xbbb6bb77,
0xb0b2b564,0xacb5b179,0xbbeabb88,0xbbfabbe2,0x3c003c00,0x96480000,0x3c003c00,0xa311a248,0x3c003c00,0x9cb69a48,0x3c003c00,0xa452a3db,
0x3c003c00,0x9fdb9e48,0x3c003c00,0xa51ba4b6,0x3c003c00,0xa17fa0b6,0x3bff3c00,0xa5e4a57f,0x3c003c00,0x9fdb0000,0x3bfb3bfc,0xac6aabd9,
0x3bff3c00,0xa5e4a3db,0x3bf93bfa,0xad65ace7,0x3bfe3bff,0xa8e8a7da,0x3bf63bf7,0xae5fade2,0x3bfd3bfe,0xaadea9e3,0x3bf23bf4,0xaf59aedc,
0x3c003c00,0xa3110000,0x3bf03bf4,0xafefaf0e,0x3bfe3bff,0xa94da711,0x3be83bed,0xb0d7b067,0x3bfb3bfd,0xac6aab11,0x3bdf3be4,0xb1b6b147,
0x3bf63bf9,0xae2dad4c,0x3bd43bda,0xb294b226,0x3c003c00,0xa51b0000,0x3bdf3be6,0xb1b6b115,0x3bfc3bfe,0xaba7a91b,0x3bcf3bd7,0xb2f7b257,
0x3bf63bf9,0xae5fad1a,0x3bbc3bc6,0xb41ab396,0x3bec3bf1,0xb074afa4,0x3ba53bb1,0xb4b7b469,0x3bff3c00,0xa6ad0000,0x3bc83bd4,0xb371b2a1,
0x3bfa3bfd,0xad00aaac,0x3bac3bbb,0xb487b420,0x3bef3bf5,0xb029aeaa,0x3b8b3b9d,0xb552b4ed,0x3bde3be7,0xb1cfb0fd,0x3b653b79,0xb61ab5b6,
0x3bff3c00,0xa81f0000,0x3bab3bbc,0xb493b414,0x3bf63bfc,0xae2dac1f,0x3b813b97,0xb58db511,0x3be53bef,0xb122b01d,0x3b4f3b69,0xb682b608,
0x3bcc3bda,0xb328b226,0x3b163b33,0xb76fb6f9,0x3bfe3c00,0xa8e80000,0x3b873ba0,0xb56ab4d5,0x3bf23bfa,0xaf59ace7,0x3b4c3b6b,0xb68db5fd,
0x3bda3be8,0xb219b0e4,0x3b073b2b,0xb7a6b71b,0x3bb73bca,0xb43eb34c,0x3ab63ae0,0xb85ab817,0x3bfe3c00,0xa9b10000,0x3b5e3b80,0xb63cb593,
0x3bee3bf8,0xb042adb0,0x3b103b39,0xb785b6e3,0x3bce3be0,0xb30fb1aa,0x3ab33ae3,0xb85fb812,0x3b9e3bb7,0xb4e7b438,0x3a493a7f,0xb8f3b8ab,
0x3bfd3c00,0xaa7a0000,0x3b2f3b5a,0xb70ab64e,0x3be83bf6,0xb0d7ae78,0x3acb3aff,0xb83ab7c2,0x3bbf3bd6,0xb402b26f,0x3a543a92,0xb8e5b891,
0x3b813ba2,0xb58db4c9,0x39cd3a13,0xb982b935,0x3bfd3c00,0xab430000,0x3afb3b30,0xb7d2b705,0x3be23bf3,0xb16caf40,0x3a7e3abf,0xb8adb84d,
0x3bae3bcb,0xb47bb334,0x39eb3a37,0xb962b909,0x3b603b8a,0xb631b558,0x3946399b,0xba04b9b5,0x3bfc3c00,0xac060000,0x3ac13b02,0xb84ab7b7,
0x3bdc3bf0,0xb201b004,0x3a293a78,0xb91bb8b5,0x3b9c3bc0,0xb4f3b3f7,0x397939d4,0xb9d6b97b,0x3b3d3b70,0xb6d2b5e5,0x38b23918,0xba7aba2b,
0x3bfb3c00,0xac6a0000,0x3a813ad0,0xb8a8b832,0x3bd43bed,0xb294b067,0x39cd3a2b,0xb982b918,0x3b873bb2,0xb56ab45d,0x38fd3969,0xba41b9e5,
0x3b163b53,0xb76fb670,0x3815388c,0xbae1ba95,0x3bfa3c00,0xacce0000,0x3a3d3a99,0xb902b887,0x3bcc3be9,0xb328b0cb,0x396b39d8,0xb9e3b976,
0x3b713ba4,0xb5dfb4bd,0x387a38f6,0xbaa2ba47,0x3aeb3b33,0xb805b6f9,0x36dd37ee,0xbb3abaf3,0x3bf93c00,0xad330000,0x39f43a5e,0xb958b8d8,
0x3bc33be5,0xb3bab12e,0x39023980,0xba3db9d0,0x3b593b95,0xb654b51d,0x37dd387c,0xbaf7baa0,0x3abd3b11,0xb850b780,0x358136b5,0xbb83bb43,
0x3bf83c00,0xad970000,0x39a63a1f,0xb9aab927,0x3bba3be1,0xb426b191,0x38943922,0xba90ba23,0x3b3f3b84,0xb6c6b57c,0x36bb37f9,0xbb42baf0,
0x3a8c3aed,0xb899b802,0x341a3570,0xbbbcbb86,0x3bf73c00,0xadfb0000,0x395439dc,0xb9f8b972,0x3bb03bdc,0xb46fb1f4,0x382038bf,0xbadbba71,
0x3b243b72,0xb737b5da,0x358d36ee,0xbb81bb36,0x3a583ac6,0xb8e0b842,0x31533420,0xbbe3bbbb,0x3bf63c00,0xae5f0000,0x38fd3996,0xba41b9ba,
0x3ba53bd7,0xb4b7b257,0x374e3858,0xbb1ebab8,0x3b073b5f,0xb7a6b637,0x345735da,0xbbb3bb72,0x3a213a9c,0xb924b881,0x2cce3191,0xbbfabbe1,
0x3bf53c00,0xaec30000,0x38a3394d,0xba85b9fe,0x3b9a3bd2,0xb4ffb2b9,0x365437d8,0xbb59baf9,0x3ae83b4b,0xb80ab693,0x323234bd,0xbbd9bba4,
0x39e73a71,0xb966b8bf,0xa4522db0,0xbc00bbf8,0x3bf33c00,0xaf270000,0x38453900,0xbac4ba3f,0x3b8e3bcd,0xb546b31b,0x355236f9,0xbb8bbb33,
0x3ac73b36,0xb840b6ee,0x2f593334,0xbbf2bbcb,0x39aa3a43,0xb9a6b8fb,0xaef51a48,0xbbf4bc00,0x3bf23c00,0xaf8b0000,0x37c838b0,0xbafeba7c,
0x3b813bc7,0xb58db37d,0x344b3614,0xbbb5bb67,0x3aa53b20,0xb874b748,0x288430e4,0xbbffbbe8,0x396b3a13,0xb9e3b935,0xb263ad4c,0xbbd7bbf9,
0x3bf03c00,0xafef0000,0x36ff385d,0xbb32bab5,0x3b733bc1,0xb5d4b3df,0x327c3529,0xbbd6bb93,0x3a813b08,0xb8a8b7a1,0xa9b12d1a,0xbbfebbf9,
0x392939e1,0xba1db96d,0xb49fb160,0xbba9bbe3,0x3bef3c00,0xb0290000,0x36313807,0xbb60bae9,0x3b653bbb,0xb61ab420,0x305b3438,0xbbedbbb7,
0x3a5c3af0,0xb8dbb7f9,0xafef1e48,0xbbf0bc00,0x38e539ad,0xba54b9a4,0xb602b408,0xbb6abbbe,0x3bed3c00,0xb05b0000,0x355e375e,0xbb89bb1a,
0x3b573bb4,0xb65fb451,0x2c6a3288,0xbbfbbbd5,0x3a353ad6,0xb90cb828,0xb27cac51,0xbbd6bbfb,0x389e3976,0xba89b9d8,0xb759b558,0xbb1bbb8a,
0x3beb3c00,0xb08d0000,0x348736aa,0xbbacbb46,0x3b473bad,0xb6a4b481,0x16483099,0xbc00bbeb,0x3a0d3abc,0xb93cb852,0xb47bb080,0xbbaebbec,
0x3855393e,0xbababa0b,0xb850b69e,0xbabdbb49,0x3be93c00,0xb0be0000,0x335935f1,0xbbc9bb6e,0x3b373ba6,0xb6e8b4b1,0xac382d4c,0xbbfcbbf9,
0x39e33aa0,0xb96bb87c,0xb5b1b2d2,0xbb7abbd1,0x380a3905,0xbae8ba3b,0xb8eab7d8,0xba50baf9,0x3be73c00,0xb0f00000,0x319e3534,0xbbe0bb91,
0x3b273b9e,0xb72cb4e1,0xb042257f,0xbbeebc00,0x39b83a83,0xb999b8a6,0xb6ddb48d,0xbb3abbab,0x377a38c9,0xbb13ba69,0xb979b881,0xb9d6ba9c,
0x3be53c00,0xb1220000,0x2fbd3475,0xbbf1bbaf,0x3b163b97,0xb76fb511,0xb263a91b,0xbbd7bbfe,0x398b3a65,0xb9c5b8ce,0xb7feb5ab,0xbaeebb7b,
0x36dd388c,0xbb3aba95,0xb9fcb90e,0xb94fba33,0x3be33c00,0xb1530000,0x2c383365,0xbbfcbbc9,0x3b043b8f,0xb7b2b540,0xb43eae78,0xbbb7bbf6,
0x395d3a47,0xb9f0b8f6,0xb889b6c1,0xba97bb41,0x363c384d,0xbb5ebabf,0xba73b992,0xb8bcb9be,0x3be13c00,0xb1850000,0x217f31db,0xbc00bbdd,
0x3af13b86,0xb7f3b570,0xb546b12e,0xbb8ebbe5,0x392e3a27,0xba19b91d,0xb90cb7cd,0xba35bafc,0x3599380d,0xbb7fbae6,0xbadbba0b,0xb820b93e,
0x3bdf3c00,0xb1b60000,0xa9b1304e,0xbbfebbed,0x3ade3b7d,0xb81ab59f,0xb648b31b,0xbb5cbbcd,0x38fd3a07,0xba41b943,0xb986b867,0xb9c9baae,
0x34f33796,0xbb9cbb0b,0xbb35ba78,0xb6f4b8b5,0x3bdd3c00,0xb1e80000,0xae5f2d7e,0xbbf6bbf8,0x3acb3b74,0xb83ab5ce,0xb742b481,0xbb21bbad,
0x38cc39e5,0xba67b969,0xb9f8b8e2,0xb954ba56,0x344b3710,0xbbb5bb2e,0xbb7fbad9,0xb599b822,0x3bda3c00,0xb2190000,0xb0f028b6,0xbbe7bbff,
0x3ab63b6b,0xb85ab5fd,0xb81ab570,0xbadebb86,0x389939c3,0xba8cb98d,0xba60b956,0xb8d6b9f6,0x33403687,0xbbcbbb4e,0xbbb8bb2e,0xb432b710,
0x3bff3bff,0xa6ada648,0x3bfe3bff,0xa8e8a8b6,0x3bff3bff,0xa776a711,0x3bfe3bfe,0xa94da91b,0x3bff3bff,0xa81fa7da,0x3bfe3bfe,0xa9b1a97f,
0x3bff3bff,0xa884a852,0x3bfe3bfe,0xaa16a9e3,0x3bef3bf1,0xb029afd6,0x3bda3bdd,0xb219b1db,0x3bea3bed,0xb0a6b067,0x3bd43bd7,0xb294b257,
0x3be53be8,0xb122b0e4,0x3bce3bd1,0xb30fb2d2,0x3be03be3,0xb19eb160,0x3bc63bca,0xb389b34c,0x3bc83bce,0xb371b303,0x3b873b91,0xb56ab534,
0x3bba3bc1,0xb426b3df,0x3b733b7d,0xb5d4b59f,0x3bab3bb2,0xb493b45d,0x3b5e3b69,0xb63cb608,0x3b9a3ba2,0xb4ffb4c9,0x3b473b53,0xb6a4b670,
0x3b8b3b99,0xb552b505,0x3b073b1a,0xb7a6b75e,0x3b6f3b7d,0xb5ebb59f,0x3ade3af3,0xb81ab7ee,0x3b4f3b5f,0xb682b637,0x3ab33ac9,0xb85fb83d,
0x3b2c3b3e,0xb715b6cc,0x3a853a9c,0xb8a3b881,0x3b3a3b50,0xb6ddb67c,0x3a5c3a7c,0xb8dbb8b0,0x3b0a3b22,0xb79bb73d,0x3a193a3b,0xb92eb905,
0x3ad53af0,0xb82ab7f9,0x39d239f6,0xb97db956,0x3a9b3ab8,0xb884b858,0x398639ad,0xb9c9b9a4,0x3ad53af6,0xb82ab7e3,0x398b39ba,0xb9c5b996,
0x3a8c3ab1,0xb899b862,0x3929395b,0xba1db9f2,0x3a3d3a65,0xb902b8ce,0x38c138f6,0xba6fba47,0x39e73a13,0xb966b935,0x3855388c,0xbababa95,
0x3a5c3a8a,0xb8dbb89b,0x389938d8,0xba8cba5e,0x39f83a2b,0xb954b918,0x38153858,0xbae1bab8,0x398b39c3,0xb9c5b98d,0x371537a1,0xbb2cbb08,
0x39163951,0xba2db9fa,0x35f73687,0xbb6cbb4e,0x39d23a0f,0xb97db93a,0x371537b7,0xbb2cbb02,0x394f3992,0xb9fcb9be,0x35c83670,0xbb76bb53,
0x38c13909,0xba6fba37,0x346f351d,0xbbb0bb95,0x382a3877,0xbad5baa3,0x3219337d,0xbbdabbc7,0x39373984,0xba11b9cb,0x34cf3593,0xbba1bb80,
0x389438e7,0xba90ba52,0x327c3408,0xbbd6bbbe,0x37c8383d,0xbafebac9,0x2e9130e4,0xbbf5bbe8,0x36543710,0xbb59bb2e,0x16482aac,0xbc00bbfd,
0x388e38ec,0xba93ba4f,0x30d732a1,0xbbe8bbd4,0x3790382d,0xbb0dbad3,0x28e82e14,0xbbfebbf7,0x35eb36c1,0xbb6fbb41,0xaccea4b6,0xbbfabc00,
0x34323511,0xbbb8bb97,0xb201b036,0xbbdcbbee,0x37b23848,0xbb04bac2,0x96482bd9,0xbc00bbfc,0x35df36cc,0xbb71bb3e,0xb010ac1f,0xbbefbbfc,
0x33eb34ed,0xbbc0bb9d,0xb402b20d,0xbbbfbbdb,0x2fef31f4,0xbbf0bbdc,0xb5ebb4f9,0xbb6fbb9b,0x36313732,0xbb60bb25,0xb0f0ad7e,0xbbe7bbf8,
0x341a3529,0xbbbcbb93,0xb49fb31b,0xbba9bbcd,0x2fbd320d,0xbbf1bbdb,0xb6afb5ab,0xbb45bb7b,0xa4522aac,0xbc00bbfd,0xb850b7ac,0xbabdbb05,
0x349f35c2,0xbba9bb77,0xb4dbb365,0xbb9fbbc9,0x308d32ea,0xbbebbbd0,0xb715b5fd,0xbb2cbb6b,0x9fdb2c51,0xbc00bbfb,0xb894b812,0xba90bae3,
0xb109ad4c,0xbbe6bbf9,0xb982b90e,0xb9cdba33,0x32013444,0xbbdcbbb6,0xb721b5f1,0xbb2abb6e,0x26ad2edc,0xbbffbbf4,0xb8adb822,0xba7ebad9,
0xb05bab11,0xbbedbbfd,0xb9aab930,0xb9a6ba17,0xb4b7b2ea,0xbba5bbd0,0xba81ba1b,0xb8a8b92b,0x2d653179,0xbbf9bbe2,0xb89eb807,0xba89bae9,
0xadc99a48,0xbbf8bc00,0xb9afb92b,0xb9a1ba1b,0xb432b1aa,0xbbb8bbe0,0xba93ba27,0xb88eb91d,0xb6d2b587,0xbb3dbb82,0xbb45baf3,0xb6afb7ee,
0xa51b2cb5,0xbc00bbfa,0xb990b900,0xb9c0ba3f,0xb294af40,0xbbd4bbf3,0xba89ba13,0xb89eb935,0xb625b4bd,0xbb63bba4,0xbb47baf0,0xb6a4b7f9,
0xb865b780,0xbab0bb11,0xbbc5bb8f,0xb3a2b540,0xafefa648,0xbbf0bbff,0xba60b9dc,0xb8d6b972,0xb517b31b,0xbb96bbcd,0xbb35bad3,0xb6f4b82d,
0xb7feb693,0xbaeebb4b,0xbbc0bb84,0xb3ebb57c,0xb94ab8ab,0xba00ba7f,0xbbfdbbe9,0xaa7ab0cb,0xb340afd6,0xbbcbbbf1,0xbb0aba99,0xb79bb887,
0xb6d2b540,0xbb3dbb8f,0xbbaebb67,0xb47bb614,0xb8dbb828,0xba5cbad6,0xbbfbbbe0,0xac9cb1aa,0xba15b980,0xb933b9d0,0xbbecbbff,0x30742852,
0xb53ab303,0xbb90bbce,0xbb89bb30,0xb55eb705,0xb83ab6e3,0xbacbbb39,0xbbf2bbca,0xaf8bb34c,0xb9a1b8f6,0xb9afba47,0xbbf5bc00,0x2ec39e48,
0xbac1ba3b,0xb84ab905,0xbb92bbd0,0x352f32ea,0xb6c6b505,0xbb3fbb99,0xbbdcbba0,0xb201b4d5,0xb8fdb838,0xba41bacc,0xbbfebbfb,0x2a16ac83,
0xba50b9b1,0xb8eab99f,0xbbaebbe4,0x347b3147,0xbb4abad9,0xb699b822,0xbaf1bb5d,0x37f33642,0xb820b67c,0xbadbbb50,0xbbffbbe6,0xa884b115,
0xb9afb8f1,0xb9a1ba4b,0xbbd2bbf8,0x32c62db0,0xbae5ba56,0xb80fb8e2,0xbb2abb8c,0x3721354c,0xbbaebb58,0xb47bb659,0xba11baaa,0x3937386d,
0xb8d1b7e3,0xba64baf6,0xbbf2bc00,0x2f8ba248,0xba4db99b,0xb8eeb9b5,0xbb6fbbc1,0x35eb33df,0xbb5cbae3,0xb648b812,0xba6bbafc,0x38c737cd,
0xbbebbbb4,0xb08db451,0xb8f8b9be,0x3a453992,0xb974b89b,0xb9daba8a,0xbbb5bbed,0x344b304e,0xbad5ba33,0xb82ab90e,0xbad8bb58,0x38253659,
0xbbb3bb55,0xb457b665,0xb979ba37,0x39d63909,0xbc00bbed,0x9648b067,0xb764b8a0,0x3b183a87,0xba09b93a,0xb941ba0f,0xbb4abbaf,0x36993475,
0xbb45bab8,0xb6afb858,0xba11babf,0x3937384d,0xbbeabbab,0xb0a6b48d,0xb85ab943,0x3ab63a07,0xbbecbc00,0x30749a48,0xb493b6b5,0x3bab3b43,
0xba8cb9cb,0xb899b984,0xbab3bb46,0x385f36aa,0xbb9cbb28,0xb4f3b726,0xb91fb9fa,0x3a253951,0xbc00bbe4,0xa452b147,0xb631b828,0x3b603ad6,
0xbbb0bbee,0x346f3036,0xae5fb3df,0x3bf63bc1,0xbafeba4f,0xb7c8b8ec,0xb9f4bab5,0x3958385d,0xbbd8bb82,0xb24bb587,0xb80ab90e,0x3ae83a33,
0xbbf3bbfe,0x2f27a97f,0xb2f7b5da,0x3bcf3b72,0xbb4cbbb7,0x368d3438,0x2dc9ac1f,0x3bf83bfc,0xbb5cbac2,0xb648b848,0xb911b9fe,0x3a31394d,
0xbbf9bbc4,0xad33b3ae,0xb5b1b802,0x3b7a3aed,0xbbc5bbf9,0x33a22d1a,0xa94db26f,0x3bfe3bd6,0xbac4bb5d,0x38453642,0x346f2fa4,0x3bb03bf1,
0xbba5bb25,0xb4b7b732,0xb80fb927,0x3ae53a1f,0xbbffbbee,0x2884b036,0xb24bb5b6,0x3bd83b79,0xbb76bbd6,0x35c8326f,0x305ba7da,0x3bed3bff,
0xba19bae0,0x392e3817,0x374234c9,0x3b213ba2,0xbbd9bb77,0xb232b5c2,0xb5ebb832,0x3b6f3ad0,0xbbe8bc00,0x30d7a57f,0xa81fb288,0x3bff3bd5,
0xbb07bb95,0x37a6351d,0x34f33080,0x3b9c3bec,0xb94fba43,0x39fc38fb,0x38ea3780,0x3a503b11,0xbbf8bbb6,0xadc9b444,0xb328b64e,0x3bcc3b5a,
0xbbb7bbf8,0x343e2db0,0x3042a9e3,0x3bee3bfe,0xba7abb36,0x38b236ee,0x379034ed,0x3b0d3b9d,0xb86ab989,0x3aac39c7,0x3a0438fb,0x39463a43,
0xbc00bbe2,0x2311b179,0xac9cb414,0x3bfb3bbc,0xbb6abbd7,0x36023257,0x34b72f40,0x3ba53bf3,0xb9d2babc,0x397d3852,0x38f83775,0x3a453b14,
0xb6ddb8b5,0x3b3a3a78,0x3ae83a0b,0x380a393e,0xbbf2bbfa,0x2f8bacb5,0x2d33af0e,0x3bf93bf4,0xbb04bb9e,0x37b234e1,0x372c3451,0x3b273bb4,
0xb911ba27,0x3a31391d,0x3a0038e2,0x394a3a56,0xb4c3b796,0x3ba33b0b,0x3b8b3ae6,0x3552380d,0x4c004c00,0x26480000,0x4c004c00,0x33113248,
0x4c004c00,0x2cb62a48,0x4c004c00,0x345233db,0x4c004c00,0x2fdb2e48,0x4c004c00,0x351b34b6,0x4c004c00,0x317f30b6,0x4bff4c00,0x35e4357f,
0x4c004c00,0x2fdb0000,0x4bfb4bfc,0x3c6a3bd9,0x4bff4c00,0x35e433db,0x4bf94bfa,0x3d653ce7,0x4bfe4bff,0x38e837da,0x4bf64bf7,0x3e5f3de2,
0x4bfd4bfe,0x3ade39e3,0x4bf24bf4,0x3f593edc,0x4c004c00,0x33110000,0x4bf04bf4,0x3fef3f0e,0x4bfe4bff,0x394d3711,0x4be84bed,0x40d74067,
0x4bfb4bfd,0x3c6a3b11,0x4bdf4be4,0x41b64147,0x4bf64bf9,0x3e2d3d4c,0x4bd44bda,0x42944226,0x4c004c00,0x351b0000,0x4bdf4be6,0x41b64115,
0x4bfc4bfe,0x3ba7391b,0x4bcf4bd7,0x42f74257,0x4bf64bf9,0x3e5f3d1a,0x4bbc4bc6,0x441a4396,0x4bec4bf1,0x40743fa4,0x4ba54bb1,0x44b74469,
0x4bff4c00,0x36ad0000,0x4bc84bd4,0x437142a1,0x4bfa4bfd,0x3d003aac,0x4bac4bbb,0x44874420,0x4bef4bf5,0x40293eaa,0x4b8b4b9d,0x455244ed,
0x4bde4be7,0x41cf40fd,0x4b654b79,0x461a45b6,0x4bff4c00,0x381f0000,0x4bab4bbc,0x44934414,0x4bf64bfc,0x3e2d3c1f,0x4b814b97,0x458d4511,
0x4be54bef,0x4122401d,0x4b4f4b69,0x46824608,0x4bcc4bda,0x43284226,0x4b164b33,0x476f46f9,0x4bfe4c00,0x38e80000,0x4b874ba0,0x456a44d5,
0x4bf24bfa,0x3f593ce7,0x4b4c4b6b,0x468d45fd,0x4bda4be8,0x421940e4,0x4b074b2b,0x47a6471b,0x4bb74bca,0x443e434c,0x4ab64ae0,0x485a4817,
0x4bfe4c00,0x39b10000,0x4b5e4b80,0x463c4593,0x4bee4bf8,0x40423db0,0x4b104b39,0x478546e3,0x4bce4be0,0x430f41aa,0x4ab34ae3,0x485f4812,
0x4b9e4bb7,0x44e74438,0x4a494a7f,0x48f348ab,0x4bfd4c00,0x3a7a0000,0x4b2f4b5a,0x470a464e,0x4be84bf6,0x40d73e78,0x4acb4aff,0x483a47c2,
0x4bbf4bd6,0x4402426f,0x4a544a92,0x48e54891,0x4b814ba2,0x458d44c9,0x49cd4a13,0x49824935,0x4bfd4c00,0x3b430000,0x4afb4b30,0x47d24705,
0x4be24bf3,0x416c3f40,0x4a7e4abf,0x48ad484d,0x4bae4bcb,0x447b4334,0x49eb4a37,0x49624909,0x4b604b8a,0x46314558,0x4946499b,0x4a0449b5,
0x4bfc4c00,0x3c060000,0x4ac14b02,0x484a47b7,0x4bdc4bf0,0x42014004,0x4a294a78,0x491b48b5,0x4b9c4bc0,0x44f343f7,0x497949d4,0x49d6497b,
0x4b3d4b70,0x46d245e5,0x48b24918,0x4a7a4a2b,0x4bfb4c00,0x3c6a0000,0x4a814ad0,0x48a84832,0x4bd44bed,0x42944067,0x49cd4a2b,0x49824918,
0x4b874bb2,0x456a445d,0x48fd4969,0x4a4149e5,0x4b164b53,0x476f4670,0x4815488c,0x4ae14a95,0x4bfa4c00,0x3cce0000,0x4a3d4a99,0x49024887,
0x4bcc4be9,0x432840cb,0x496b49d8,0x49e34976,0x4b714ba4,0x45df44bd,0x487a48f6,0x4aa24a47,0x4aeb4b33,0x480546f9,0x46dd47ee,0x4b3a4af3,
0x4bf94c00,0x3d330000,0x49f44a5e,0x495848d8,0x4bc34be5,0x43ba412e,0x49024980,0x4a3d49d0,0x4b594b95,0x4654451d,0x47dd487c,0x4af74aa0,
0x4abd4b11,0x48504780,0x458146b5,0x4b834b43,0x4bf84c00,0x3d970000,0x49a64a1f,0x49aa4927,0x4bba4be1,0x44264191,0x48944922,0x4a904a23,
0x4b3f4b84,0x46c6457c,0x46bb47f9,0x4b424af0,0x4a8c4aed,0x48994802,0x441a4570,0x4bbc4b86,0x4bf74c00,0x3dfb0000,0x495449dc,0x49f84972,
0x4bb04bdc,0x446f41f4,0x482048bf,0x4adb4a71,0x4b244b72,0x473745da,0x458d46ee,0x4b814b36,0x4a584ac6,0x48e04842,0x41534420,0x4be34bbb,
0x4bf64c00,0x3e5f0000,0x48fd4996,0x4a4149ba,0x4ba54bd7,0x44b74257,0x474e4858,0x4b1e4ab8,0x4b074b5f,0x47a64637,0x445745da,0x4bb34b72,
0x4a214a9c,0x49244881,0x3cce4191,0x4bfa4be1,0x4bf54c00,0x3ec30000,0x48a3494d,0x4a8549fe,0x4b9a4bd2,0x44ff42b9,0x465447d8,0x4b594af9,
0x4ae84b4b,0x480a4693,0x423244bd,0x4bd94ba4,0x49e74a71,0x496648bf,0xb4523db0,0x4c004bf8,0x4bf34c00,0x3f270000,0x48454900,0x4ac44a3f,
0x4b8e4bcd,0x4546431b,0x455246f9,0x4b8b4b33,0x4ac74b36,0x484046ee,0x3f594334,0x4bf24bcb,0x49aa4a43,0x49a648fb,0xbef52a48,0x4bf44c00,
0x4bf24c00,0x3f8b0000,0x47c848b0,0x4afe4a7c,0x4b814bc7,0x458d437d,0x444b4614,0x4bb54b67,0x4aa54b20,0x48744748,0x388440e4,0x4bff4be8,
0x496b4a13,0x49e34935,0xc263bd4c,0x4bd74bf9,0x4bf04c00,0x3fef0000,0x46ff485d,0x4b324ab5,0x4b734bc1,0x45d443df,0x427c4529,0x4bd64b93,
0x4a814b08,0x48a847a1,0xb9b13d1a,0x4bfe4bf9,0x492949e1,0x4a1d496d,0xc49fc160,0x4ba94be3,0x4bef4c00,0x40290000,0x46314807,0x4b604ae9,
0x4b654bbb,0x461a4420,0x405b4438,0x4bed4bb7,0x4a5c4af0,0x48db47f9,0xbfef2e48,0x4bf04c00,0x48e549ad,0x4a5449a4,0xc602c408,0x4b6a4bbe,
0x4bed4c00,0x405b0000,0x455e475e,0x4b894b1a,0x4b574bb4,0x465f4451,0x3c6a4288,0x4bfb4bd5,0x4a354ad6,0x490c4828,0xc27cbc51,0x4bd64bfb,
0x489e4976,0x4a8949d8,0xc759c558,0x4b1b4b8a,0x4beb4c00,0x408d0000,0x448746aa,0x4bac4b46,0x4b474bad,0x46a44481,0x26484099,0x4c004beb,
0x4a0d4abc,0x493c4852,0xc47bc080,0x4bae4bec,0x4855493e,0x4aba4a0b,0xc850c69e,0x4abd4b49,0x4be94c00,0x40be0000,0x435945f1,0x4bc94b6e,
0x4b374ba6,0x46e844b1,0xbc383d4c,0x4bfc4bf9,0x49e34aa0,0x496b487c,0xc5b1c2d2,0x4b7a4bd1,0x480a4905,0x4ae84a3b,0xc8eac7d8,0x4a504af9,
0x4be74c00,0x40f00000,0x419e4534,0x4be04b91,0x4b274b9e,0x472c44e1,0xc042357f,0x4bee4c00,0x49b84a83,0x499948a6,0xc6ddc48d,0x4b3a4bab,
0x477a48c9,0x4b134a69,0xc979c881,0x49d64a9c,0x4be54c00,0x41220000,0x3fbd4475,0x4bf14baf,0x4b164b97,0x476f4511,0xc263b91b,0x4bd74bfe,
0x498b4a65,0x49c548ce,0xc7fec5ab,0x4aee4b7b,0x46dd488c,0x4b3a4a95,0xc9fcc90e,0x494f4a33,0x4be34c00,0x41530000,0x3c384365,0x4bfc4bc9,
0x4b044b8f,0x47b24540,0xc43ebe78,0x4bb74bf6,0x495d4a47,0x49f048f6,0xc889c6c1,0x4a974b41,0x463c484d,0x4b5e4abf,0xca73c992,0x48bc49be,
0x4be14c00,0x41850000,0x317f41db,0x4c004bdd,0x4af14b86,0x47f34570,0xc546c12e,0x4b8e4be5,0x492e4a27,0x4a19491d,0xc90cc7cd,0x4a354afc,
0x4599480d,0x4b7f4ae6,0xcadbca0b,0x4820493e,0x4bdf4c00,0x41b60000,0xb9b1404e,0x4bfe4bed,0x4ade4b7d,0x481a459f,0xc648c31b,0x4b5c4bcd,
0x48fd4a07,0x4a414943,0xc986c867,0x49c94aae,0x44f34796,0x4b9c4b0b,0xcb35ca78,0x46f448b5,0x4bdd4c00,0x41e80000,0xbe5f3d7e,0x4bf64bf8,
0x4acb4b74,0x483a45ce,0xc742c481,0x4b214bad,0x48cc49e5,0x4a674969,0xc9f8c8e2,0x49544a56,0x444b4710,0x4bb54b2e,0xcb7fcad9,0x45994822,
0x4bda4c00,0x42190000,0xc0f038b6,0x4be74bff,0x4ab64b6b,0x485a45fd,0xc81ac570,0x4ade4b86,0x489949c3,0x4a8c498d,0xca60c956,0x48d649f6,
0x43404687,0x4bcb4b4e,0xcbb8cb2e,0x44324710,0x4bd84c00,0x424b0000,0xc2adb248,0x4bd34c00,0x4aa24b62,0x487a462b,0xc88ec659,0x4a934b58,
0x4865499f,0x4ab049b1,0xcabdc9c3,0x4850498d,0x41e845fd,0x4bdd4b6b,0xcbe1cb74,0x418545ce,0x4bd64c00,0x427c0000,0xc432bbd9,0x4bb84bfc,
0x4a8c4b58,0x48994659,0xc8fdc73d,0x4a414b22,0x4830497b,0x4ad149d4,0xcb10ca27,0x4785491d,0x408d4570,0x4beb4b86,0xcbf9cbad,0x3d334481,
0x4bd34c00,0x42ad0000,0xc50bbf0e,0x4b984bf4,0x4a764b4e,0x48b74687,0xc966c80d,0x49e74ae6,0x47f34956,0x4af149f6,0xcb57ca83,0x465f48a6,
0x3e5f44e1,0x4bf64b9e,0xcc00cbd7,0xb17f4257,0x4bd04c00,0x42de0000,0xc5dfc115,0x4b714be6,0x4a604b43,0x48d646b5,0xc9c9c877,0x49864aa3,
0x47854930,0x4b104a17,0xcb92cad6,0x452f4828,0x3b434451,0x4bfd4bb4,0xcbf5cbf3,0xbe913f40,0x4bce4c00,0x430f0000,0xc6afc2a1,0x4b454bd4,
0x4a494b39,0x48f346e3,0xca25c8dd,0x491f4a5a,0x47154909,0x4b2c4a37,0xcbc0cb20,0x43eb4748,0x3311437d,0x4c004bc7,0xcbd9cbff,0xc2323711,
0x4bcb4c00,0x43400000,0xc77ac414,0x4b134bbc,0x4a314b2e,0x49114710,0xca7ac93e,0x48b24a0b,0x46a448e2,0x4b474a56,0xcbe2cb5f,0x416c4637,
0xb7764257,0x4bff4bd7,0xcbaccbfd,0xc487bb75,0x4bc84c00,0x43710000,0xc820c4d5,0x4adb4ba0,0x4a194b22,0x492e473d,0xcac7c99b,0x484049b5,
0x463148ba,0x4b604a74,0xcbf8cb95,0x3dc9451d,0xbc9c412e,0x4bfb4be5,0xcb6fcbeb,0xc5ebc099,0x4bc54c00,0x43a20000,0xc87fc593,0x4a9e4b80,
0x4a004b17,0x494a476a,0xcb0dc9f2,0x4790495b,0x45bc4891,0x4b784a92,0xcc00cbc0,0x317f43f7,0xbf594004,0x4bf24bf0,0xcb21cbca,0xc742c34c,
0x4bc24c00,0x43d30000,0xc8dbc64e,0x4a5c4b5a,0x49e74b0b,0x49664796,0xcb4aca43,0x469948fb,0x45464867,0x4b8e4aae,0xcbfbcbe0,0xbc6a41aa,
0xc1093db0,0x4be64bf8,0xcac4cb9b,0xc845c4f9,0x4bbf4c00,0x44020000,0xc933c705,0x4a154b30,0x49cd4aff,0x498247c2,0xcb7fca8e,0x45994896,
0x44cf483d,0x4ba14ac9,0xcbe9cbf5,0xc0be3eaa,0xc2633aac,0x4bd74bfd,0xca58cb5d,0xc8e0c642,0x4bbc4c00,0x441a0000,0xc986c7b7,0x49c94b02,
0x49b34af3,0x499d47ee,0xcbabcad3,0x4493482d,0x44574812,0x4bb34ae3,0xcbcbcbff,0xc34037da,0xc3ba33db,0x4bc34c00,0xc9dfcb11,0xc970c780,
0x4bb84c00,0x44320000,0xc9d6c832,0x49794ad0,0x49994ae6,0x49b8480d,0xcbcecb11,0x430f4780,0x43ba47cd,0x4bc34afc,0xcb9fcbfe,0xc4dbb97f,
0xc487b57f,0x4bac4c00,0xc958cab8,0xc9f4c858,0x4bb54c00,0x444b0000,0xca21c887,0x49244a99,0x497d4ad9,0x49d24822,0xcbe7cb49,0x40f0469e,
0x42c64775,0x4bd24b14,0xcb68cbf2,0xc60ebf72,0xc52fbb75,0x4b924bfd,0xc8c7ca52,0xca6bc8e7,0x4bb24c00,0x44630000,0xca67c8d8,0x48cc4a5e,
0x49624acc,0x49eb4838,0xcbf8cb79,0x3d9745b6,0x41cf471b,0x4bde4b2b,0xcb24cbdb,0xc737c20d,0xc5d4be14,0x4b734bf7,0xc82ac9e1,0xcad5c96d,
0x4bae4c00,0x447b0000,0xcaa9c927,0x486f4a1f,0x49464abf,0x4a04484d,0xcc00cba2,0x351b44c9,0x40d746c1,0x4be84b41,0xcad5cbb9,0xc82ac42c,
0xc676c036,0x4b524bee,0xc70ac964,0xcb2fc9e9,0x4bab4c00,0x44930000,0xcae5c972,0x480f49dc,0x49294ab1,0x4a1d4862,0xcbfecbc4,0xba1643ae,
0x3fbd4665,0x4bf14b55,0xca7acb8c,0xc8b2c54c,0xc715c160,0x4b2c4be3,0xc5b1c8dd,0xcb7aca5a,0x4ba74c00,0x44ab0000,0xcb1bc9ba,0x47594996,
0x490c4aa3,0x4a354877,0xcbf2cbdf,0xbf5941c3,0x3dc94608,0x4bf84b69,0xca15cb55,0xc933c665,0xc7b2c288,0x4b044bd5,0xc44bc84d,0xcbb5cabf,
0x4ba34c00,0x44c30000,0xcb4cc9fe,0x468d494d,0x48ee4a95,0x4a4d488c,0xcbdecbf1,0xc1cf3fa4,0x3ba745ab,0x4bfc4b7b,0xc9a6cb14,0xc9aac775,
0xc825c3ae,0x4ad84bc4,0xc1b6c76a,0xcbdfcb17,0x4b9f4c00,0x44db0000,0xcb78ca3f,0x45bc4900,0x48d14a87,0x4a6448a0,0xcbc0cbfd,0xc3eb3b75,
0x3776454c,0x4bff4b8c,0xc92ecac9,0xca19c83d,0xc86fc469,0x4aa94bb1,0xbd97c62b,0xcbf8cb62,0x4b9c4c00,0x44f30000,0xcb9eca7c,0x44e748b0,
0x48b24a78,0x4a7a48b5,0xcb9acc00,0xc4ffaa48,0xa64844ed,0x4c004b9d,0xc8adca74,0xca7ec8ba,0xc8b7c4f9,0x4a764b9b,0x2cb6c4e1,0xcc00cb9e,
0x4b984c00,0x450b0000,0xcbbdcab5,0x440e485d,0x48944a69,0x4a9048c9,0xcb6acbfc,0xc602bc1f,0xb81f448d,0x4bff4bab,0xc825ca17,0xcad8c930,
0xc8fdc587,0x4a414b82,0x3e2dc31b,0xcbf6cbcd,0x4b944c00,0x45230000,0xcbd7cae9,0x42634807,0x48744a5a,0x4aa548dd,0xcb32cbf0,0xc6ffc004,
0xbc06442c,0x4bfc4bb9,0xc72cc9b1,0xcb27c99f,0xc941c614,0x4a094b67,0x4201c067,0xcbdccbed,0x4b904c00,0x453a0000,0xcbeacb1a,0x40a6475e,
0x48554a4b,0x4aba48f1,0xcaf1cbdc,0xc7f3c1f4,0xbdfb4396,0x4bf74bc6,0xc602c943,0xcb6aca07,0xc982c69e,0x49cd4b49,0x446fbaac,0xcbb0cbfd,
0x4b8b4c00,0x45520000,0xcbf8cb46,0x3dc946aa,0x48354a3b,0x4ace4905,0xcaa9cbc1,0xc86fc3df,0xbfef42d2,0x4bf04bd1,0xc4cfc8ce,0xcba1ca65,
0xc9c0c726,0x49904b28,0x45d43852,0xcb73cbff,0x4b874c00,0x456a0000,0xcbffcb6e,0x388445f1,0x48154a2b,0x4ae14918,0xca58cb9e,0xc8e0c4e1,
0xc0f0420d,0x4be74bdb,0xc328c852,0xcbcccabc,0xc9fcc7ac,0x494f4b05,0x472c3fa4,0xcb27cbf1,0x4b834c00,0x45810000,0xcc00cb91,0xb51b4534,
0x47e84a1b,0x4af4492b,0xca00cb74,0xc94ac5ce,0xc1e84147,0x4bdd4be4,0xc0a6c7a1,0xcbeacb08,0xca35c817,0x490c4ae0,0x483a4288,0xcacbcbd5,
0x4b7f4c00,0x45990000,0xcbfacbaf,0xbcce4475,0x47a64a0b,0x4b07493e,0xc9a1cb43,0xc9afc6b5,0xc2de4080,0x4bd04bec,0xbc38c693,0xcbfccb4b,
0xca6bc858,0x48c74ab8,0x48d64499,0xca60cbaa,0x4b7a4c00,0x45b10000,0xcbefcbc9,0xc0294365,0x476449fa,0x4b184951,0xc93ccb0b,0xca0dc796,
0xc3d33f72,0x4bc24bf2,0x3311c57c,0xcc00cb84,0xca9ec896,0x487f4a8e,0x496645e5,0xc9e7cb70,0x4b764c00,0x45c80000,0xcbddcbdd,0xc1e841db,
0x472149e9,0x4b2a4964,0xc8d1cacc,0xca64c838,0xc4633de2,0x4bb24bf7,0x3dfbc45d,0xcbf7cbb2,0xcacec8d3,0x48354a62,0x49eb4726,0xc962cb28,
0x4b714c00,0x45df0000,0xcbc5cbed,0xc3a2404e,0x46dd49d8,0x4b3a4976,0xc85fca87,0xcab3c8a0,0xc4db3c51,0x4b9f4bfb,0x4185c26f,0xcbe1cbd6,
0xcafbc90e,0x47d24a33,0x4a64482d,0xc8d1cad3,0x4b6c4c00,0x45f70000,0xcba7cbf8,0xc4ab3d7e,0x469949c7,0x4b4a4989,0xc7d2ca3b,0xcafbc905,
0xc552397f,0x4b8b4bfe,0x4402c01d,0xcbbfcbef,0xcb24c948,0x47374a02,0x4ace48bf,0xc835ca71,0x4b684c00,0x460e0000,0xcb83cbff,0xc58138b6,
0x465449b5,0x4b59499b,0xc6ddc9e9,0xcb3ac964,0xc5c834b6,0x4b764c00,0x453abb11,0xcb90cbfd,0xcb4ac980,0x469949d0,0x4b2a4948,0xc721ca02,
0x2c002c00,0x2c002c00,0x2c002c00,0x2c002c00,0x2b642c00,0x261f29a8,0xa61f0000,0xab64a9a8,0x29a82c00,0xa9a80000,0xa9a8ac00,0x29a80000,
0x261f2c00,0xab64a9a8,0x2b640000,0xa61f29a8,0x2c00,0xac00,0x2c00,0xac00,0xa61f2c00,0x2b64a9a8,0xab640000,0x261f29a8,
0xa9a82c00,0x29a80000,0x29a8ac00,0xa9a80000,0xab642c00,0xa61f29a8,0x261f0000,0x2b64a9a8,0,0,0,0,
0x261f0000,0x2b6429a8,0x2b642c00,0x261f29a8,0x29a80000,0x29a82c00,0xa9a80000,0xa9a8ac00,0x2b640000,0xa61f29a8,0xa61fac00,0x2b6429a8,
0x2c000000,0xac000000,0x2c000000,0xac000000,0x2b640000,0xa61fa9a8,0xa61f2c00,0x2b64a9a8,0x29a80000,0x29a8ac00,0xa9a80000,0xa9a82c00,
0x261f0000,0x2b64a9a8,0x2b64ac00,0x261fa9a8,0xac002c00,0xac002c00,0xac002c00,0xac002c00,0xab642c00,0xa61f29a8,0x261f0000,0x2b64a9a8,
0xa9a82c00,0x29a80000,0x29a8ac00,0xa9a80000,0xa61f2c00,0x2b64a9a8,0xab640000,0x261f29a8,0x2c00,0xac00,0x2c00,0xac00,
0x261f2c00,0xab64a9a8,0x2b640000,0xa61f29a8,0x29a82c00,0xa9a80000,0xa9a8ac00,0x29a80000,0x2b642c00,0x261f29a8,0xa61f0000,0xab64a9a8,
0,0,0,0,0xa61f0000,0xab6429a8,0xab642c00,0xa61f29a8,0xa9a80000,0xa9a82c00,0x29a80000,0x29a8ac00,
0xab640000,0x261f29a8,0x261fac00,0xab6429a8,0xac000000,0x2c000000,0xac000000,0x2c000000,0xab640000,0x261fa9a8,0x261f2c00,0xab64a9a8,
0xa9a80000,0xa9a8ac00,0x29a80000,0x29a82c00,0xa61f0000,0xab64a9a8,0xab64ac00,0xa61fa9a8,0,0,0,0,
0xa61f0000,0xab64a9a8,0xab64ac00,0xa61fa9a8,0xa9a80000,0xa9a8ac00,0x29a80000,0x29a82c00,0xab640000,0x261fa9a8,0x261f2c00,0xab64a9a8,
0xac000000,0x2c000000,0xac000000,0x2c000000,0xab640000,0x261f29a8,0x261fac00,0xab6429a8,0xa9a80000,0xa9a82c00,0x29a80000,0x29a8ac00,
0xa61f0000,0xab6429a8,0xab642c00,0xa61f29a8,0x2c002c00,0x2c002c00,0x2c002c00,0x2c002c00,0x2b642c00,0x261f29a8,0xa61f0000,0xab64a9a8,
0x29a82c00,0xa9a80000,0xa9a8ac00,0x29a80000,0x261f2c00,0xab64a9a8,0x2b640000,0xa61f29a8,0x2c00,0xac00,0x2c00,0xac00,
0xa61f2c00,0x2b64a9a8,0xab640000,0x261f29a8,0xa9a82c00,0x29a80000,0x29a8ac00,0xa9a80000,0xab642c00,0xa61f29a8,0x261f0000,0x2b64a9a8,
0,0,0,0,0x261f0000,0x2b64a9a8,0x2b64ac00,0x261fa9a8,0x29a80000,0x29a8ac00,0xa9a80000,0xa9a82c00,
0x2b640000,0xa61fa9a8,0xa61f2c00,0x2b64a9a8,0x2c000000,0xac000000,0x2c000000,0xac000000,0x2b640000,0xa61f29a8,0xa61fac00,0x2b6429a8,
0x29a80000,0x29a82c00,0xa9a80000,0xa9a8ac00,0x261f0000,0x2b6429a8,0x2b642c00,0x261f29a8,0xac002c00,0xac002c00,0xac002c00,0xac002c00,
0xab642c00,0xa61f29a8,0x261f0000,0x2b64a9a8,0xa9a82c00,0x29a80000,0x29a8ac00,0xa9a80000,0xa61f2c00,0x2b64a9a8,0xab640000,0x261f29a8,
0x2c00,0xac00,0x2c00,0xac00,0x261f2c00,0xab64a9a8,0x2b640000,0xa61f29a8,0x29a82c00,0xa9a80000,0xa9a8ac00,0x29a80000,
0x2b642c00,0x261f29a8,0xa61f0000,0xab64a9a8,0x2c002c00,0x2c002c00,0x2c002c00,0x2c002c00,0xab64ac00,0xa61fa9a8,0x261f0000,0x2b6429a8,
0x29a82c00,0xa9a80000,0xa9a8ac00,0x29a80000,0xa61fac00,0x2b6429a8,0xab640000,0x261fa9a8,0x2c00,0xac00,0x2c00,0xac00,
0x261fac00,0xab6429a8,0x2b640000,0xa61fa9a8,0xa9a82c00,0x29a80000,0x29a8ac00,0xa9a80000,0x2b64ac00,0x261fa9a8,0xa61f0000,0xab6429a8,
0,0,0,0,0xa61f0000,0xab64a9a8,0xab64ac00,0xa61fa9a8,0x29a80000,0x29a82c00,0xa9a80000,0xa9a8ac00,
0xab640000,0x261fa9a8,0x261f2c00,0xab64a9a8,0x2c000000,0xac000000,0x2c000000,0xac000000,0xab640000,0x261f29a8,0x261fac00,0xab6429a8,
0x29a80000,0x29a8ac00,0xa9a80000,0xa9a82c00,0xa61f0000,0xab6429a8,0xab642c00,0xa61f29a8,0xac002c00,0xac002c00,0xac002c00,0xac002c00,
0x2b64ac00,0x261fa9a8,0xa61f0000,0xab6429a8,0xa9a82c00,0x29a80000,0x29a8ac00,0xa9a80000,0x261fac00,0xab6429a8,0x2b640000,0xa61fa9a8,
0x2c00,0xac00,0x2c00,0xac00,0xa61fac00,0x2b6429a8,0xab640000,0x261fa9a8,0x29a82c00,0xa9a80000,0xa9a8ac00,0x29a80000,
0xab64ac00,0xa61fa9a8,0x261f0000,0x2b6429a8,0,0,0,0,0x261f0000,0x2b64a9a8,0x2b64ac00,0x261fa9a8,
0xa9a80000,0xa9a82c00,0x29a80000,0x29a8ac00,0x2b640000,0xa61fa9a8,0xa61f2c00,0x2b64a9a8,0xac000000,0x2c000000,0xac000000,0x2c000000,
0x2b640000,0xa61f29a8,0xa61fac00,0x2b6429a8,0xa9a80000,0xa9a8ac00,0x29a80000,0x29a82c00,0x261f0000,0x2b6429a8,0x2b642c00,0x261f29a8,
0,0,0,0,0x261f0000,0x2b6429a8,0x2b642c00,0x261f29a8,0xa9a80000,0xa9a8ac00,0x29a80000,0x29a82c00,
0x2b640000,0xa61f29a8,0xa61fac00,0x2b6429a8,0xac000000,0x2c000000,0xac000000,0x2c000000,0x2b640000,0xa61fa9a8,0xa61f2c00,0x2b64a9a8,
0xa9a80000,0xa9a82c00,0x29a80000,0x29a8ac00,0x261f0000,0x2b64a9a8,0x2b64ac00,0x261fa9a8,0x2c002c00,0x2c002c00,0x2c002c00,0x2c002c00,
0xab64ac00,0xa61fa9a8,0x261f0000,0x2b6429a8,0x29a82c00,0xa9a80000,0xa9a8ac00,0x29a80000,0xa61fac00,0x2b6429a8,0xab640000,0x261fa9a8,
0x2c00,0xac00,0x2c00,0xac00,0x261fac00,0xab6429a8,0x2b640000,0xa61fa9a8,0xa9a82c00,0x29a80000,0x29a8ac00,0xa9a80000,
0x2b64ac00,0x261fa9a8,0xa61f0000,0xab6429a8,0,0,0,0,0xa61f0000,0xab6429a8,0xab642c00,0xa61f29a8,
0x29a80000,0x29a8ac00,0xa9a80000,0xa9a82c00,0xab640000,0x261f29a8,0x261fac00,0xab6429a8,0x2c000000,0xac000000,0x2c000000,0xac000000,
0xab640000,0x261fa9a8,0x261f2c00,0xab64a9a8,0x29a80000,0x29a82c00,0xa9a80000,0xa9a8ac00,0xa61f0000,0xab64a9a8,0xab64ac00,0xa61fa9a8,
0xac002c00,0xac002c00,0xac002c00,0xac002c00,0x2b64ac00,0x261fa9a8,0xa61f0000,0xab6429a8,0xa9a82c00,0x29a80000,0x29a8ac00,0xa9a80000,
0x261fac00,0xab6429a8,0x2b640000,0xa61fa9a8,0x2c00,0xac00,0x2c00,0xac00,0xa61fac00,0x2b6429a8,0xab640000,0x261fa9a8,
0x29a82c00,0xa9a80000,0xa9a8ac00,0x29a80000,0xab64ac00,0xa61fa9a8,0x261f0000,0x2b6429a8,0x2bd92c00,0x2aa72b64,0x287229a8,0x223e261f,
0x2aa72c00,0xa23e261f,0xabd9a9a8,0xa872ab64,0x28722c00,0xabd9a61f,0x223ea9a8,0x2aa72b64,0x223e2c00,0xa872ab64,0x2aa729a8,0xabd9a61f,
0xa23e2c00,0x2872ab64,0xaaa729a8,0x2bd9a61f,0xa8722c00,0x2bd9a61f,0xa23ea9a8,0xaaa72b64,0xaaa72c00,0x223e261f,0x2bd9a9a8,0x2872ab64,
0xabd92c00,0xaaa72b64,0xa87229a8,0xa23e261f,0x223e0000,0x2872261f,0x2aa729a8,0x2bd92b64,0x28720000,0x2bd92b64,0x223e29a8,0xaaa7a61f,
0x2aa70000,0x223e2b64,0xabd9a9a8,0x2872a61f,0x2bd90000,0xaaa7261f,0x2872a9a8,0xa23e2b64,0x2bd90000,0xaaa7a61f,0x287229a8,0xa23eab64,
0x2aa70000,0x223eab64,0xabd929a8,0x2872261f,0x28720000,0x2bd9ab64,0x223ea9a8,0xaaa7261f,0x223e0000,0x2872a61f,0x2aa7a9a8,0x2bd9ab64,
0xabd92c00,0xaaa72b64,0xa87229a8,0xa23e261f,0xaaa72c00,0x223e261f,0x2bd9a9a8,0x2872ab64,0xa8722c00,0x2bd9a61f,0xa23ea9a8,0xaaa72b64,
0xa23e2c00,0x2872ab64,0xaaa729a8,0x2bd9a61f,0x223e2c00,0xa872ab64,0x2aa729a8,0xabd9a61f,0x28722c00,0xabd9a61f,0x223ea9a8,0x2aa72b64,
0x2aa72c00,0xa23e261f,0xabd9a9a8,0xa872ab64,0x2bd92c00,0x2aa72b64,0x287229a8,0x223e261f,0xa23e0000,0xa872261f,0xaaa729a8,0xabd92b64,
0xa8720000,0xabd92b64,0xa23e29a8,0x2aa7a61f,0xaaa70000,0xa23e2b64,0x2bd9a9a8,0xa872a61f,0xabd90000,0x2aa7261f,0xa872a9a8,0x223e2b64,
0xabd90000,0x2aa7a61f,0xa87229a8,0x223eab64,0xaaa70000,0xa23eab64,0x2bd929a8,0xa872261f,0xa8720000,0xabd9ab64,0xa23ea9a8,0x2aa7261f,
0xa23e0000,0xa872a61f,0xaaa7a9a8,0xabd9ab64,0xa23e0000,0xa872a61f,0xaaa7a9a8,0xabd9ab64,0xa8720000,0xabd9ab64,0xa23ea9a8,0x2aa7261f,
0xaaa70000,0xa23eab64,0x2bd929a8,0xa872261f,0xabd90000,0x2aa7a61f,0xa87229a8,0x223eab64,0xabd90000,0x2aa7261f,0xa872a9a8,0x223e2b64,
0xaaa70000,0xa23e2b64,0x2bd9a9a8,0xa872a61f,0xa8720000,0xabd92b64,0xa23e29a8,0x2aa7a61f,0xa23e0000,0xa872261f,0xaaa729a8,0xabd92b64,
0x2bd92c00,0x2aa72b64,0x287229a8,0x223e261f,0x2aa72c00,0xa23e261f,0xabd9a9a8,0xa872ab64,0x28722c00,0xabd9a61f,0x223ea9a8,0x2aa72b64,
0x223e2c00,0xa872ab64,0x2aa729a8,0xabd9a61f,0xa23e2c00,0x2872ab64,0xaaa729a8,0x2bd9a61f,0xa8722c00,0x2bd9a61f,0xa23ea9a8,0xaaa72b64,
0xaaa72c00,0x223e261f,0x2bd9a9a8,0x2872ab64,0xabd92c00,0xaaa72b64,0xa87229a8,0xa23e261f,0x223e0000,0x2872a61f,0x2aa7a9a8,0x2bd9ab64,
0x28720000,0x2bd9ab64,0x223ea9a8,0xaaa7261f,0x2aa70000,0x223eab64,0xabd929a8,0x2872261f,0x2bd90000,0xaaa7a61f,0x287229a8,0xa23eab64,
0x2bd90000,0xaaa7261f,0x2872a9a8,0xa23e2b64,0x2aa70000,0x223e2b64,0xabd9a9a8,0x2872a61f,0x28720000,0x2bd92b64,0x223e29a8,0xaaa7a61f,
0x223e0000,0x2872261f,0x2aa729a8,0x2bd92b64,0xabd92c00,0xaaa72b64,0xa87229a8,0xa23e261f,0xaaa72c00,0x223e261f,0x2bd9a9a8,0x2872ab64,
0xa8722c00,0x2bd9a61f,0xa23ea9a8,0xaaa72b64,0xa23e2c00,0x2872ab64,0xaaa729a8,0x2bd9a61f,0x223e2c00,0xa872ab64,0x2aa729a8,0xabd9a61f,
0x28722c00,0xabd9a61f,0x223ea9a8,0x2aa72b64,0x2aa72c00,0xa23e261f,0xabd9a9a8,0xa872ab64,0x2bd92c00,0x2aa72b64,0x287229a8,0x223e261f,
0xa23e0000,0xa872a61f,0xaaa7a9a8,0xabd9ab64,0x28720000,0x2bd92b64,0x223e29a8,0xaaa7a61f,0xaaa70000,0xa23eab64,0x2bd929a8,0xa872261f,
0x2bd90000,0xaaa7261f,0x2872a9a8,0xa23e2b64,0xabd90000,0x2aa7261f,0xa872a9a8,0x223e2b64,0x2aa70000,0x223eab64,0xabd929a8,0x2872261f,
0xa8720000,0xabd92b64,0xa23e29a8,0x2aa7a61f,0x223e0000,0x2872a61f,0x2aa7a9a8,0x2bd9ab64,0x2bd92c00,0x2aa72b64,0x287229a8,0x223e261f,
0xaaa7ac00,0x223ea61f,0x2bd929a8,0x28722b64,0x28722c00,0xabd9a61f,0x223ea9a8,0x2aa72b64,0xa23eac00,0x28722b64,0xaaa7a9a8,0x2bd9261f,
0xa23e2c00,0x2872ab64,0xaaa729a8,0x2bd9a61f,0x2872ac00,0xabd9261f,0x223e29a8,0x2aa7ab64,0xaaa72c00,0x223e261f,0x2bd9a9a8,0x2872ab64,
0x2bd9ac00,0x2aa7ab64,0x2872a9a8,0x223ea61f,0x223e0000,0x2872a61f,0x2aa7a9a8,0x2bd9ab64,0xa8720000,0xabd92b64,0xa23e29a8,0x2aa7a61f,
0x2aa70000,0x223eab64,0xabd929a8,0x2872261f,0xabd90000,0x2aa7261f,0xa872a9a8,0x223e2b64,0x2bd90000,0xaaa7261f,0x2872a9a8,0xa23e2b64,
0xaaa70000,0xa23eab64,0x2bd929a8,0xa872261f,0x28720000,0x2bd92b64,0x223e29a8,0xaaa7a61f,0xa23e0000,0xa872a61f,0xaaa7a9a8,0xabd9ab64,
0xabd92c00,0xaaa72b64,0xa87229a8,0xa23e261f,0x2aa7ac00,0xa23ea61f,0xabd929a8,0xa8722b64,0xa8722c00,0x2bd9a61f,0xa23ea9a8,0xaaa72b64,
0x223eac00,0xa8722b64,0x2aa7a9a8,0xabd9261f,0x223e2c00,0xa872ab64,0x2aa729a8,0xabd9a61f,0xa872ac00,0x2bd9261f,0xa23e29a8,0xaaa7ab64,
0x2aa72c00,0xa23e261f,0xabd9a9a8,0xa872ab64,0xabd9ac00,0xaaa7ab64,0xa872a9a8,0xa23ea61f,0xabd9ac00,0xaaa7ab64,0xa872a9a8,0xa23ea61f,
0x2aa72c00,0xa23e261f,0xabd9a9a8,0xa872ab64,0xa872ac00,0x2bd9261f,0xa23e29a8,0xaaa7ab64,0x223e2c00,0xa872ab64,0x2aa729a8,0xabd9a61f,
0x223eac00,0xa8722b64,0x2aa7a9a8,0xabd9261f,0xa8722c00,0x2bd9a61f,0xa23ea9a8,0xaaa72b64,0x2aa7ac00,0xa23ea61f,0xabd929a8,0xa8722b64,
0xabd92c00,0xaaa72b64,0xa87229a8,0xa23e261f,0xa23e0000,0xa872a61f,0xaaa7a9a8,0xabd9ab64,0x28720000,0x2bd92b64,0x223e29a8,0xaaa7a61f,
0xaaa70000,0xa23eab64,0x2bd929a8,0xa872261f,0x2bd90000,0xaaa7261f,0x2872a9a8,0xa23e2b64,0xabd90000,0x2aa7261f,0xa872a9a8,0x223e2b64,
0x2aa70000,0x223eab64,0xabd929a8,0x2872261f,0xa8720000,0xabd92b64,0xa23e29a8,0x2aa7a61f,0x223e0000,0x2872a61f,0x2aa7a9a8,0x2bd9ab64,
0x2bd9ac00,0x2aa7ab64,0x2872a9a8,0x223ea61f,0xaaa72c00,0x223e261f,0x2bd9a9a8,0x2872ab64,0x2872ac00,0xabd9261f,0x223e29a8,0x2aa7ab64,
0xa23e2c00,0x2872ab64,0xaaa729a8,0x2bd9a61f,0xa23eac00,0x28722b64,0xaaa7a9a8,0x2bd9261f,0x28722c00,0xabd9a61f,0x223ea9a8,0x2aa72b64,
0xaaa7ac00,0x223ea61f,0x2bd929a8,0x28722b64,0x2bd92c00,0x2aa72b64,0x287229a8,0x223e261f,0x223e0000,0x2872a61f,0x2aa7a9a8,0x2bd9ab64,
0xa8720000,0xabd92b64,0xa23e29a8,0x2aa7a61f,0x2aa70000,0x223eab64,0xabd929a8,0x2872261f,0xabd90000,0x2aa7261f,0xa872a9a8,0x223e2b64,
0x2bd90000,0xaaa7261f,0x2872a9a8,0xa23e2b64,0xaaa70000,0xa23eab64,0x2bd929a8,0xa872261f,0x28720000,0x2bd92b64,0x223e29a8,0xaaa7a61f,
0xa23e0000,0xa872a61f,0xaaa7a9a8,0xabd9ab64,0x27fe2800,0x96480000,0x273b2764,0xa2d7a21f,0x27ea27f6,0x9cb29a46,0x26dd270e,0xa41da38b,
0x27c327d9,0x9fc69e3e,0x266d26a7,0xa4c4a472,0x278827a8,0xa164a0a5,0x25ed262f,0xa55fa513,0x27c32800,0x9fc60000,0xa4c4a21f,0xa66da764,
0x25ed270e,0xa55fa38b,0xa73ba62f,0xa2d7a513,0x21642472,0xa788a6a7,0xa7fea7d9,0x16489e3e,0x9cb21a46,0xa7eaa7f6,0xa6dda7a8,0x241d20a5,
0x273b2800,0xa2d70000,0xa55fa764,0x25ed221f,0x1fc62513,0xa7c3a62f,0x1cb2a0a5,0x27ea27a8,0xa4c49e3e,0xa66da7d9,0x26dd2472,0x241d26a7,
0xa7fea70e,0x9648a38b,0x278827f6,0xa1641a46,0x266d2800,0xa4c40000,0x26dd221f,0x241d2764,0xa16420a5,0xa788a7a8,0x25ed27f6,0xa55f9a46,
0xa7fea6a7,0x1648a472,0xa2d71e3e,0xa73ba7d9,0x9fc6a62f,0x27c32513,0xa7eaa70e,0x1cb2a38b,0x255f2800,0xa5ed0000,0x21642764,0xa788a21f,
0xa66d9a46,0xa4c4a7f6,0xa7c3a38b,0x9fc6a70e,0xa41da7d9,0x26dd1e3e,0x9cb2a6a7,0x27ea2472,0x273b20a5,0x22d727a8,0x27fe2513,0x1648262f,
0x241d2800,0xa6dd0000,0xa7eaa21f,0x9cb2a764,0xa7fea38b,0x9648a70e,0x2164a513,0x2788262f,0x22d7a472,0x273b26a7,0x255f27d9,0xa5ed1e3e,
0x24c427f6,0xa66d1a46,0xa7c3a0a5,0x9fc6a7a8,0x21642800,0xa7880000,0x1648a764,0x27fe221f,0xa6dda62f,0x241da513,0x24c427a8,0xa66d20a5,
0x27ea1e3e,0x1cb227d9,0xa7c3a472,0x1fc6a6a7,0xa55f238b,0xa5eda70e,0x273b9a46,0x22d727f6,0x1cb22800,0xa7ea0000,0x27c3221f,0x9fc62764,
0xa2d7a7a8,0x273ba0a5,0xa7fe9a46,0x9648a7f6,0x255f26a7,0xa5ed2472,0x27889e3e,0x216427d9,0xa6dda513,0x241da62f,0xa66d238b,0xa4c4a70e,
0x96482800,0xa7fe0000,0xa2d72764,0xa73ba21f,0x1cb2a7f6,0x27ea1a46,0x241da70e,0x26dd238b,0x9fc627d9,0xa7c39e3e,0xa4c426a7,0xa66da472,
0x2164a7a8,0x278820a5,0x255fa62f,0x25ed2513,0x9fc62800,0xa7c30000,0xa66da21f,0x24c4a764,0x255fa70e,0x25ed238b,0x22d7262f,0xa73b2513,
0xa7882472,0xa164a6a7,0x1648a7d9,0x27fe9e3e,0x27ea9a46,0x9cb227f6,0xa41d27a8,0xa6dda0a5,0xa2d72800,0xa73b0000,0x25eda764,0x255f221f,
0x27c3a513,0x1fc6262f,0xa7ea20a5,0x1cb2a7a8,0xa66d9e3e,0x24c4a7d9,0x241d2472,0xa6dd26a7,0x1648270e,0xa7fe238b,0x2164a7f6,0x27889a46,
0xa4c42800,0xa66d0000,0x241d221f,0xa6dd2764,0x2788a0a5,0xa16427a8,0x255fa7f6,0x25ed1a46,0x1648a6a7,0x27fea472,0xa73b1e3e,0x22d7a7d9,
0xa7c3262f,0x9fc6a513,0x9cb2270e,0xa7ea238b,0xa5ed2800,0xa55f0000,0xa7882764,0xa164a21f,0x24c41a46,0xa66d27f6,0x1fc6238b,0xa7c3270e,
0x26dda7d9,0x241d1e3e,0x27eaa6a7,0x1cb22472,0xa2d7a0a5,0x273ba7a8,0x9648a513,0x27fea62f,0xa6dd2800,0xa41d0000,0x9cb2a21f,0x27eaa764,
0x1648238b,0xa7fe270e,0xa7882513,0x2164a62f,0x273ba472,0xa2d726a7,0xa5ed27d9,0xa55f1e3e,0x266da7f6,0x24c49a46,0x1fc620a5,0xa7c327a8,
0xa7882800,0xa1640000,0x27fea764,0x9648221f,0xa41d262f,0xa6dd2513,0x266da7a8,0x24c4a0a5,0x1cb21e3e,0xa7ea27d9,0x1fc6a472,0x27c3a6a7,
0x25eda38b,0xa55f270e,0xa2d71a46,0x273ba7f6,0xa7ea2800,0x9cb20000,0x9fc6221f,0xa7c32764,0xa73b27a8,0xa2d720a5,0x16481a46,0xa7fe27f6,
0xa5ed26a7,0xa55f2472,0x21649e3e,0xa78827d9,0xa41d2513,0xa6dd262f,0x24c4a38b,0xa66d270e,0xa7fe2800,0x16480000,0xa73b2764,0x22d7a21f,
0xa7ea27f6,0x1cb29a46,0xa6dd270e,0x241da38b,0xa7c327d9,0x1fc69e3e,0xa66d26a7,0x24c4a472,0xa78827a8,0x2164a0a5,0xa5ed262f,0x255fa513,
0xa7c32800,0x1fc60000,0x24c4a21f,0x266da764,0xa5ed270e,0x255fa38b,0x273ba62f,0x22d7a513,0xa1642472,0x2788a6a7,0x27fea7d9,0x96489e3e,
0x1cb21a46,0x27eaa7f6,0x26dda7a8,0xa41d20a5,0xa73b2800,0x22d70000,0x255fa764,0xa5ed221f,0x9fc62513,0x27c3a62f,0x9cb2a0a5,0xa7ea27a8,
0x24c49e3e,0x266da7d9,0xa6dd2472,0xa41d26a7,0x27fea70e,0x1648a38b,0xa78827f6,0x21641a46,0xa66d2800,0x24c40000,0xa6dd221f,0xa41d2764,
0x216420a5,0x2788a7a8,0xa5ed27f6,0x255f9a46,0x27fea6a7,0x9648a472,0x22d71e3e,0x273ba7d9,0x1fc6a62f,0xa7c32513,0x27eaa70e,0x9cb2a38b,
0xa55f2800,0x25ed0000,0xa1642764,0x2788a21f,0x266d9a46,0x24c4a7f6,0x27c3a38b,0x1fc6a70e,0x241da7d9,0xa6dd1e3e,0x1cb2a6a7,0xa7ea2472,
0xa73b20a5,0xa2d727a8,0xa7fe2513,0x9648262f,0xa41d2800,0x26dd0000,0x27eaa21f,0x1cb2a764,0x27fea38b,0x1648a70e,0xa164a513,0xa788262f,
0xa2d7a472,0xa73b26a7,0xa55f27d9,0x25ed1e3e,0xa4c427f6,0x266d1a46,0x27c3a0a5,0x1fc6a7a8,0xa1642800,0x27880000,0x9648a764,0xa7fe221f,
0x26dda62f,0xa41da513,0xa4c427a8,0x266d20a5,0xa7ea1e3e,0x9cb227d9,0x27c3a472,0x9fc6a6a7,0x255f238b,0x25eda70e,0xa73b9a46,0xa2d727f6,
0x9cb22800,0x27ea0000,0xa7c3221f,0x1fc62764,0x22d7a7a8,0xa73ba0a5,0x27fe9a46,0x1648a7f6,0xa55f26a7,0x25ed2472,0xa7889e3e,0xa16427d9,
0x26dda513,0xa41da62f,0x266d238b,0x24c4a70e,0x16482800,0x27fe0000,0x22d72764,0x273ba21f,0x9cb2a7f6,0xa7ea1a46,0xa41da70e,0xa6dd238b,
0x1fc627d9,0x27c39e3e,0x24c426a7,0x266da472,0xa164a7a8,0xa78820a5,0xa55fa62f,0xa5ed2513,0x1fc62800,0x27c30000,0x266da21f,0xa4c4a764,
0xa55fa70e,0xa5ed238b,0xa2d7262f,0x273b2513,0x27882472,0x2164a6a7,0x9648a7d9,0xa7fe9e3e,0xa7ea9a46,0x1cb227f6,0x241d27a8,0x26dda0a5,
0x22d72800,0x273b0000,0xa5eda764,0xa55f221f,0xa7c3a513,0x9fc6262f,0x27ea20a5,0x9cb2a7a8,0x266d9e3e,0xa4c4a7d9,0xa41d2472,0x26dd26a7,
0x9648270e,0x27fe238b,0xa164a7f6,0xa7889a46,0x24c42800,0x266d0000,0xa41d221f,0x26dd2764,0xa788a0a5,0x216427a8,0xa55fa7f6,0xa5ed1a46,
0x9648a6a7,0xa7fea472,0x273b1e3e,0xa2d7a7d9,0x27c3262f,0x1fc6a513,0x1cb2270e,0x27ea238b,0x25ed2800,0x255f0000,0x27882764,0x2164a21f,
0xa4c41a46,0x266d27f6,0x9fc6238b,0x27c3270e,0xa6dda7d9,0xa41d1e3e,0xa7eaa6a7,0x9cb22472,0x22d7a0a5,0xa73ba7a8,0x1648a513,0xa7fea62f,
0x26dd2800,0x241d0000,0x1cb2a21f,0xa7eaa764,0x9648238b,0x27fe270e,0x27882513,0xa164a62f,0xa73ba472,0x22d726a7,0x25ed27d9,0x255f1e3e,
0xa66da7f6,0xa4c49a46,0x9fc620a5,0x27c327a8,0x27882800,0x21640000,0xa7fea764,0x1648221f,0x241d262f,0x26dd2513,0xa66da7a8,0xa4c4a0a5,
0x9cb21e3e,0x27ea27d9,0x9fc6a472,0xa7c3a6a7,0xa5eda38b,0x255f270e,0x22d71a46,0xa73ba7f6,0x27ea2800,0x1cb20000,0x1fc6221f,0x27c32764,
0x273b27a8,0x22d720a5,0x96481a46,0x27fe27f6,0x25ed26a7,0x255f2472,0xa1649e3e,0x278827d9,0x241d2513,0x26dd262f,0xa4c4a38b,0x266d270e,
0x255f25a8,0xa5eda5a8,0x2164221f,0xa788a764,0x24c42513,0xa66da62f,0x1fc620a5,0xa7c3a7a8,0x241d2472,0xa6dda6a7,0x1cb21e3e,0xa7eaa7d9,
0x22d7238b,0xa73ba70e,0x16481a46,0xa7fea7f6,0xa41da5a8,0x26dd25a8,0x27ea2764,0x1cb2221f,0x9648a0a5,0x27fe27a8,0x278827f6,0xa1649a46,
0x22d71e3e,0x273b27d9,0x255f26a7,0xa5eda472,0x266d2513,0x24c4262f,0x1fc6238b,0xa7c3a70e,0x216425a8,0xa788a5a8,0x1648a21f,0x27fe2764,
0xa41d9a46,0xa6dda7f6,0x266d238b,0x24c4270e,0xa7eaa6a7,0x9cb2a472,0x27c327d9,0x9fc61e3e,0xa5eda7a8,0x255f20a5,0x22d7262f,0xa73ba513,
0x9cb2a5a8,0x27ea25a8,0xa7c3a764,0x1fc6a21f,0x273b238b,0x22d7270e,0x9648a513,0x27fe262f,0x255f27d9,0xa5ed9e3e,0x27882472,0x216426a7,
0xa41d1a46,0xa6dda7f6,0x24c427a8,0xa66da0a5,0x964825a8,0xa7fea5a8,0xa2d7221f,0xa73ba764,0xa7eaa62f,0x1cb2a513,0xa6dda7a8,0x241da0a5,
0x1fc6a472,0x27c326a7,0x24c49e3e,0x266d27d9,0x2788270e,0xa164238b,0x25ed27f6,0xa55f1a46,0x1fc6a5a8,0x27c325a8,0x266d2764,0xa4c4221f,
0x25ed27a8,0xa55f20a5,0xa73b9a46,0xa2d7a7f6,0xa7889e3e,0xa164a7d9,0x1648a6a7,0x27fe2472,0x1cb2a62f,0x27ea2513,0x26dd270e,0xa41d238b,
0xa2d725a8,0xa73ba5a8,0x25eda21f,0x255f2764,0x9fc6a7f6,0x27c31a46,0x9cb2270e,0xa7eaa38b,0x266d26a7,0xa4c42472,0xa41da7d9,0x26dd9e3e,
0xa7fea0a5,0x9648a7a8,0x27882513,0xa164262f,0x24c4a5a8,0x266d25a8,0xa41da764,0x26dda21f,0xa164270e,0xa788a38b,0x25ed262f,0xa55f2513,
0x1648a7d9,0x27fe1e3e,0xa73ba472,0x22d7a6a7,0x1fc627f6,0xa7c31a46,0x27ea20a5,0x9cb227a8,0xa5ed25a8,0xa55fa5a8,0xa788221f,0xa164a764,
0x266da513,0x24c4262f,0x27c3a0a5,0x1fc627a8,0xa6dd2472,0xa41da6a7,0xa7ea1e3e,0x9cb2a7d9,0x273ba38b,0x22d7270e,0x27fe9a46,0x164827f6,
0x26dda5a8,0x241d25a8,0x1cb22764,0xa7ea221f,0xa7fe20a5,0x9648a7a8,0x2164a7f6,0x27881a46,0x273b1e3e,0xa2d727d9,0xa5ed26a7,0xa55fa472,
0xa4c4a513,0x266da62f,0x27c3a38b,0x1fc6270e,0xa78825a8,0xa164a5a8,0x27fea21f,0x96482764,0x26dd1a46,0xa41d27f6,0xa4c4a38b,0x266da70e,
0x9cb2a6a7,0x27eaa472,0x9fc627d9,0xa7c31e3e,0xa55f27a8,0xa5eda0a5,0x273ba62f,0x22d72513,0x27eaa5a8,0x1cb225a8,0x1fc6a764,0x27c3a21f,
0xa2d7a38b,0x273ba70e,0xa7fe2513,0x9648a62f,0xa5ed27d9,0xa55f9e3e,0x21642472,0xa78826a7,0x26dd9a46,0xa41d27f6,0x266da7a8,0x24c420a5,
0xa7fe25a8,0x1648a5a8,0xa73b221f,0x22d7a764,0x9cb2262f,0xa7ea2513,0xa41d27a8,0xa6dd20a5,0x27c3a472,0x9fc626a7,0x266d9e3e,0xa4c427d9,
0x2164a70e,0x2788a38b,0x255fa7f6,0x25ed9a46,0x27c3a5a8,0x9fc625a8,0xa4c42764,0xa66d221f,0x255fa7a8,0x25eda0a5,0x22d71a46,0xa73b27f6,
0xa1649e3e,0x2788a7d9,0x27fea6a7,0x96482472,0xa7ea262f,0x1cb2a513,0x241da70e,0x26dda38b,0xa73b25a8,0x22d7a5a8,0x255fa21f,0xa5ed2764,
0xa7c327f6,0x9fc69a46,0x27eaa70e,0x9cb2238b,0xa4c426a7,0xa66d2472,0x26dda7d9,0x241d9e3e,0x164820a5,0xa7fe27a8,0x2164a513,0x2788a62f,
0x266da5a8,0xa4c425a8,0x26dda764,0x241da21f,0x2788a70e,0xa164238b,0x255fa62f,0x25eda513,0x27fea7d9,0x96481e3e,0x22d7a472,0x273ba6a7,
0x27c3a7f6,0x1fc69a46,0x1cb2a0a5,0x27eaa7a8,0xa55f25a8,0x25eda5a8,0xa164221f,0x2788a764,0xa4c42513,0x266da62f,0x9fc620a5,0x27c3a7a8,
0xa41d2472,0x26dda6a7,0x9cb21e3e,0x27eaa7d9,0xa2d7238b,0x273ba70e,0x96481a46,0x27fea7f6,0x241da5a8,0xa6dd25a8,0xa7ea2764,0x9cb2221f,
0x1648a0a5,0xa7fe27a8,0xa78827f6,0x21649a46,0xa2d71e3e,0xa73b27d9,0xa55f26a7,0x25eda472,0xa66d2513,0xa4c4262f,0x9fc6238b,0x27c3a70e,
0xa16425a8,0x2788a5a8,0x9648a21f,0xa7fe2764,0x241d9a46,0x26dda7f6,0xa66d238b,0xa4c4270e,0x27eaa6a7,0x1cb2a472,0xa7c327d9,0x1fc61e3e,
0x25eda7a8,0xa55f20a5,0xa2d7262f,0x273ba513,0x1cb2a5a8,0xa7ea25a8,0x27c3a764,0x9fc6a21f,0xa73b238b,0xa2d7270e,0x1648a513,0xa7fe262f,
0xa55f27d9,0x25ed9e3e,0xa7882472,0xa16426a7,0x241d1a46,0x26dda7f6,0xa4c427a8,0x266da0a5,0x164825a8,0x27fea5a8,0x22d7221f,0x273ba764,
0x27eaa62f,0x9cb2a513,0x26dda7a8,0xa41da0a5,0x9fc6a472,0xa7c326a7,0xa4c49e3e,0xa66d27d9,0xa788270e,0x2164238b,0xa5ed27f6,0x255f1a46,
0x9fc6a5a8,0xa7c325a8,0xa66d2764,0x24c4221f,0xa5ed27a8,0x255f20a5,0x273b9a46,0x22d7a7f6,0x27889e3e,0x2164a7d9,0x9648a6a7,0xa7fe2472,
0x9cb2a62f,0xa7ea2513,0xa6dd270e,0x241d238b,0x22d725a8,0x273ba5a8,0xa5eda21f,0xa55f2764,0x1fc6a7f6,0xa7c31a46,0x1cb2270e,0x27eaa38b,
0xa66d26a7,0x24c42472,0x241da7d9,0xa6dd9e3e,0x27fea0a5,0x1648a7a8,0xa7882513,0x2164262f,0xa4c4a5a8,0xa66d25a8,0x241da764,0xa6dda21f,
0x2164270e,0x2788a38b,0xa5ed262f,0x255f2513,0x9648a7d9,0xa7fe1e3e,0x273ba472,0xa2d7a6a7,0x9fc627f6,0x27c31a46,0xa7ea20a5,0x1cb227a8,
0x25ed25a8,0x255fa5a8,0x2788221f,0x2164a764,0xa66da513,0xa4c4262f,0xa7c3a0a5,0x9fc627a8,0x26dd2472,0x241da6a7,0x27ea1e3e,0x1cb2a7d9,
0xa73ba38b,0xa2d7270e,0xa7fe9a46,0x964827f6,0xa6dda5a8,0xa41d25a8,0x9cb22764,0x27ea221f,0x27fe20a5,0x1648a7a8,0xa164a7f6,0xa7881a46,
0xa73b1e3e,0x22d727d9,0x25ed26a7,0x255fa472,0x24c4a513,0xa66da62f,0xa7c3a38b,0x9fc6270e,0x278825a8,0x2164a5a8,0xa7fea21f,0x16482764,
0xa6dd1a46,0x241d27f6,0x24c4a38b,0xa66da70e,0x1cb2a6a7,0xa7eaa472,0x1fc627d9,0x27c31e3e,0x255f27a8,0x25eda0a5,0xa73ba62f,0xa2d72513,
0xa7eaa5a8,0x9cb225a8,0x9fc6a764,0xa7c3a21f,0x22d7a38b,0xa73ba70e,0x27fe2513,0x1648a62f,0x25ed27d9,0x255f9e3e,0xa1642472,0x278826a7,
0xa6dd9a46,0x241d27f6,0xa66da7a8,0xa4c420a5,0x27fe25a8,0x9648a5a8,0x273b221f,0xa2d7a764,0x1cb2262f,0x27ea2513,0x241d27a8,0x26dd20a5,
0xa7c3a472,0x1fc626a7,0xa66d9e3e,0x24c427d9,0xa164a70e,0xa788a38b,0xa55fa7f6,0xa5ed9a46,0xa7c3a5a8,0x1fc625a8,0x24c42764,0x266d221f,
0xa55fa7a8,0xa5eda0a5,0xa2d71a46,0x273b27f6,0x21649e3e,0xa788a7d9,0xa7fea6a7,0x16482472,0x27ea262f,0x9cb2a513,0xa41da70e,0xa6dda38b,
0x273b25a8,0xa2d7a5a8,0xa55fa21f,0x25ed2764,0x27c327f6,0x1fc69a46,0xa7eaa70e,0x1cb2238b,0x24c426a7,0x266d2472,0xa6dda7d9,0xa41d9e3e,
0x964820a5,0x27fe27a8,0xa164a513,0xa788a62f,0xa66da5a8,0x24c425a8,0xa6dda764,0xa41da21f,0xa788a70e,0x2164238b,0xa55fa62f,0xa5eda513,
0xa7fea7d9,0x16481e3e,0xa2d7a472,0xa73ba6a7,0xa7c3a7f6,0x9fc69a46,0x9cb2a0a5,0xa7eaa7a8,
};

#define PROF(slot) do {} while (0)
#define PROF3(slot) do {} while (0)
#define PROF2(slot) do {} while (0)

__device__ __forceinline__ uint32_t smem_u32(const void* p) { return (uint32_t)__cvta_generic_to_shared(p); }

__device__ __forceinline__ void mbar_init(uint32_t a, uint32_t c) {
  asm volatile("mbarrier.init.shared::cta.b64 [%0], %1;\n" ::"r"(a), "r"(c) : "memory");
}
__device__ __forceinline__ void mbar_expect_tx(uint32_t a, uint32_t bytes) {
  asm volatile("mbarrier.arrive.expect_tx.shared::cta.b64 _, [%0], %1;\n" ::"r"(a), "r"(bytes) : "memory");
}
__device__ __forceinline__ void mbar_arrive_cluster(uint32_t cluster_addr) {
  asm volatile("mbarrier.arrive.shared::cluster.b64 _, [%0];\n" ::"r"(cluster_addr) : "memory");
}
__device__ __forceinline__ void mbar_arrive_cluster_n(uint32_t cluster_addr, uint32_t n) {
  asm volatile("mbarrier.arrive.shared::cluster.b64 _, [%0], %1;\n" ::"r"(cluster_addr), "r"(n) : "memory");
}
__device__ __forceinline__ bool mbar_try(uint32_t a, uint32_t parity) {
  uint32_t ok;
  asm volatile("{\n.reg .pred p;\nmbarrier.try_wait.parity.shared::cta.b64 p, [%1], %2;\nselp.u32 %0, 1, 0, p;\n}\n"
               : "=r"(ok) : "r"(a), "r"(parity) : "memory");
  return ok;
}
__device__ __forceinline__ void mbar_wait(uint32_t a, uint32_t parity) {
  if (mbar_try(a, parity)) return;
#pragma unroll 1
  for (int n = 0; n < SPIN_LIMIT; n++)
    if (mbar_try(a, parity)) break;
}
__device__ __forceinline__ void mbar_wait_idle(uint32_t a, uint32_t parity) {
#pragma unroll 1
  for (int n = 0; n < SPIN_LIMIT; n++) {
    uint32_t ok;
    asm volatile("{\n.reg .pred p;\nmbarrier.try_wait.parity.shared::cta.b64 p, [%1], %2, %3;\nselp.u32 %0, 1, 0, p;\n}\n"
                 : "=r"(ok) : "r"(a), "r"(parity), "r"(4000) : "memory");
    if (ok) break;
  }
}
__device__ __forceinline__ bool elect_one() {
  uint32_t p;
  asm volatile("{\n.reg .pred P;\nelect.sync _|P, 0xffffffff;\nselp.u32 %0, 1, 0, P;\n}\n" : "=r"(p));
  return p;
}
__device__ __forceinline__ uint32_t mapa(uint32_t a, uint32_t rank) {
  uint32_t r;
  asm volatile("mapa.shared::cluster.u32 %0, %1, %2;\n" : "=r"(r) : "r"(a), "r"(rank));
  return r;
}
__device__ __forceinline__ void nb_sync(int id, int n) { asm volatile("bar.sync %0, %1;\n" ::"r"(id), "r"(n) : "memory"); }
__device__ __forceinline__ void nb_arrive(int id, int n) { asm volatile("bar.arrive %0, %1;\n" ::"r"(id), "r"(n) : "memory"); }
__device__ __forceinline__ void cluster_sync_all() {
  asm volatile("barrier.cluster.arrive.relaxed.aligned;\nbarrier.cluster.wait.aligned;\n" ::: "memory");
}
__device__ __forceinline__ void fence_async_smem() { asm volatile("fence.proxy.async.shared::cta;\n" ::: "memory"); }
__device__ __forceinline__ void fence_async_all() { asm volatile("fence.proxy.async.global;\n" ::: "memory"); }

__device__ __forceinline__ void tma_load_3d(uint32_t dst, const CUtensorMap* tm, uint32_t bar, int c0, int c1, int c2) {
  asm volatile(
      "cp.async.bulk.tensor.3d.shared::cluster.global.mbarrier::complete_tx::bytes [%0], [%1, {%3, %4, %5}], [%2];\n"
      ::"r"(dst), "l"(tm), "r"(bar), "r"(c0), "r"(c1), "r"(c2) : "memory");
}
__device__ __forceinline__ void tma_load_4d(uint32_t dst, const CUtensorMap* tm, uint32_t bar, int c0, int c1, int c2, int c3) {
  asm volatile(
      "cp.async.bulk.tensor.4d.shared::cluster.global.mbarrier::complete_tx::bytes [%0], [%1, {%3, %4, %5, %6}], [%2];\n"
      ::"r"(dst), "l"(tm), "r"(bar), "r"(c0), "r"(c1), "r"(c2), "r"(c3) : "memory");
}
__device__ __forceinline__ void tma_load_3d_mc(uint32_t dst, const CUtensorMap* tm, uint32_t bar, int c0, int c1, int c2) {
  asm volatile(
      "cp.async.bulk.tensor.3d.shared::cluster.global.mbarrier::complete_tx::bytes.multicast::cluster [%0], [%1, {%3, %4, %5}], [%2], %6;\n"
      ::"r"(dst), "l"(tm), "r"(bar), "r"(c0), "r"(c1), "r"(c2), "h"((uint16_t)3) : "memory");
}
__device__ __forceinline__ void tma_load_5d(uint32_t dst, const CUtensorMap* tm, uint32_t bar, int c0, int c4) {
  asm volatile(
      "cp.async.bulk.tensor.5d.shared::cluster.global.mbarrier::complete_tx::bytes [%0], [%1, {%3, %5, %5, %5, %4}], [%2];\n"
      ::"r"(dst), "l"(tm), "r"(bar), "r"(c0), "r"(c4), "r"(0) : "memory");
}
__device__ __forceinline__ void bulk_load(uint32_t dst, const void* src, uint32_t bytes, uint32_t bar) {
  asm volatile("cp.async.bulk.shared::cluster.global.mbarrier::complete_tx::bytes [%0], [%1], %2, [%3];\n"
               ::"r"(dst), "l"(src), "r"(bytes), "r"(bar) : "memory");
}
__device__ __forceinline__ void bulk_commit() { asm volatile("cp.async.bulk.commit_group;\n" ::: "memory"); }
__device__ __forceinline__ void bulk_wait0() { asm volatile("cp.async.bulk.wait_group 0;\n" ::: "memory"); }
__device__ __forceinline__ void prefetch_tmap(const CUtensorMap* tm) {
  asm volatile("prefetch.tensormap [%0];\n" ::"l"(tm) : "memory");
}

__device__ __forceinline__ void wg_fence() { asm volatile("wgmma.fence.sync.aligned;\n" ::: "memory"); }
__device__ __forceinline__ void wg_commit() { asm volatile("wgmma.commit_group.sync.aligned;\n" ::: "memory"); }
template <int N> __device__ __forceinline__ void wg_wait() {
  asm volatile("wgmma.wait_group.sync.aligned %0;\n" ::"n"(N) : "memory");
}
__device__ __forceinline__ uint64_t mkdesc(uint32_t addr, uint32_t lbo, uint32_t sbo, uint32_t swz) {
  return (uint64_t)((addr & 0x3FFFF) >> 4) | ((uint64_t)(lbo >> 4) << 16) | ((uint64_t)(sbo >> 4) << 32) |
         ((uint64_t)swz << 62);
}

#define R4(d, o) "+f"(d[o + 0]), "+f"(d[o + 1]), "+f"(d[o + 2]), "+f"(d[o + 3])
#define R8(d, o) R4(d, o), R4(d, o + 4)
#define R16(d, o) R8(d, o), R8(d, o + 8)
#define R32(d, o) R16(d, o), R16(d, o + 16)
#define R64(d, o) R32(d, o), R32(d, o + 32)

__device__ __forceinline__ void wgmma_n192(float (&d)[96], uint64_t da, uint64_t db, uint32_t acc) {
  asm volatile(
      "{\n.reg .pred p;\nsetp.ne.u32 p, %98, 0;\n"
      "wgmma.mma_async.sync.aligned.m64n192k16.f32.bf16.bf16 "
      "{%0,%1,%2,%3,%4,%5,%6,%7,%8,%9,%10,%11,%12,%13,%14,%15,%16,%17,%18,%19,%20,%21,%22,%23,%24,%25,%26,%27,%28,%29,%30,%31,"
      "%32,%33,%34,%35,%36,%37,%38,%39,%40,%41,%42,%43,%44,%45,%46,%47,%48,%49,%50,%51,%52,%53,%54,%55,%56,%57,%58,%59,%60,%61,%62,%63,"
      "%64,%65,%66,%67,%68,%69,%70,%71,%72,%73,%74,%75,%76,%77,%78,%79,%80,%81,%82,%83,%84,%85,%86,%87,%88,%89,%90,%91,%92,%93,%94,%95}, "
      "%96, %97, p, 1, 1, 0, 1;\n}\n"
      : R64(d, 0), R32(d, 64)
      : "l"(da), "l"(db), "r"(acc));
}
__device__ __forceinline__ void wgmma_n128(float (&d)[64], uint64_t da, uint64_t db, uint32_t acc) {
  asm volatile(
      "{\n.reg .pred p;\nsetp.ne.u32 p, %66, 0;\n"
      "wgmma.mma_async.sync.aligned.m64n128k16.f32.bf16.bf16 "
      "{%0,%1,%2,%3,%4,%5,%6,%7,%8,%9,%10,%11,%12,%13,%14,%15,%16,%17,%18,%19,%20,%21,%22,%23,%24,%25,%26,%27,%28,%29,%30,%31,"
      "%32,%33,%34,%35,%36,%37,%38,%39,%40,%41,%42,%43,%44,%45,%46,%47,%48,%49,%50,%51,%52,%53,%54,%55,%56,%57,%58,%59,%60,%61,%62,%63}, "
      "%64, %65, p, 1, 1, 0, 1;\n}\n"
      : R64(d, 0)
      : "l"(da), "l"(db), "r"(acc));
}
template <int N> __device__ __forceinline__ void fence_regs(float (&d)[N]) {
#pragma unroll
  for (int i = 0; i < N; i++) asm volatile("" : "+f"(d[i])::"memory");
}

__device__ __forceinline__ void mma16816(float (&d)[4], uint32_t a0, uint32_t a1, uint32_t a2, uint32_t a3, uint32_t b0,
                                         uint32_t b1) {
  asm("mma.sync.aligned.m16n8k16.row.col.f32.bf16.bf16.f32 {%0,%1,%2,%3}, {%4,%5,%6,%7}, {%8,%9}, {%0,%1,%2,%3};\n"
      : "+f"(d[0]), "+f"(d[1]), "+f"(d[2]), "+f"(d[3])
      : "r"(a0), "r"(a1), "r"(a2), "r"(a3), "r"(b0), "r"(b1));
}
__device__ __forceinline__ void mma16816_z(float (&d)[4], uint32_t a0, uint32_t a1, uint32_t a2, uint32_t a3, uint32_t b0,
                                           uint32_t b1) {
  asm("mma.sync.aligned.m16n8k16.row.col.f32.bf16.bf16.f32 {%0,%1,%2,%3}, {%4,%5,%6,%7}, {%8,%9}, {%10,%10,%10,%10};\n"
      : "=f"(d[0]), "=f"(d[1]), "=f"(d[2]), "=f"(d[3])
      : "r"(a0), "r"(a1), "r"(a2), "r"(a3), "r"(b0), "r"(b1), "f"(0.f));
}
__device__ __forceinline__ void ldsm4t(uint32_t (&r)[4], uint32_t a) {
  asm volatile("ldmatrix.sync.aligned.m8n8.x4.trans.shared.b16 {%0,%1,%2,%3}, [%4];\n"
               : "=r"(r[0]), "=r"(r[1]), "=r"(r[2]), "=r"(r[3]) : "r"(a) : "memory");
}
__device__ __forceinline__ void ldsm2t(uint32_t& r0, uint32_t& r1, uint32_t a) {
  asm volatile("ldmatrix.sync.aligned.m8n8.x2.trans.shared.b16 {%0,%1}, [%2];\n" : "=r"(r0), "=r"(r1) : "r"(a) : "memory");
}
__device__ __forceinline__ void st_async128(uint32_t a, uint32_t bar, uint32_t x, uint32_t y, uint32_t z, uint32_t w) {
  asm volatile("st.async.weak.shared::cluster.mbarrier::complete_tx::bytes.v4.b32 [%0], {%2,%3,%4,%5}, [%1];\n"
               ::"r"(a), "r"(bar), "r"(x), "r"(y), "r"(z), "r"(w) : "memory");
}
__device__ __forceinline__ void mbar_arrive(uint32_t a) {
  asm volatile("mbarrier.arrive.shared::cta.b64 _, [%0];\n" ::"r"(a) : "memory");
}
__device__ __forceinline__ void stsm4(uint32_t a, uint32_t r0, uint32_t r1, uint32_t r2, uint32_t r3) {
  asm volatile("stmatrix.sync.aligned.m8n8.x4.shared.b16 [%0], {%1,%2,%3,%4};\n"
               ::"r"(a), "r"(r0), "r"(r1), "r"(r2), "r"(r3) : "memory");
}
__device__ __forceinline__ void stsm4t(uint32_t a, uint32_t r0, uint32_t r1, uint32_t r2, uint32_t r3) {
  asm volatile("stmatrix.sync.aligned.m8n8.x4.trans.shared.b16 [%0], {%1,%2,%3,%4};\n"
               ::"r"(a), "r"(r0), "r"(r1), "r"(r2), "r"(r3) : "memory");
}
__device__ __forceinline__ uint2 lds64(uint32_t a) {
  uint2 v;
  asm volatile("ld.shared.v2.u32 {%0,%1}, [%2];\n" : "=r"(v.x), "=r"(v.y) : "r"(a));
  return v;
}
__device__ __forceinline__ uint4 lds128(uint32_t a) {
  uint4 v;
  asm volatile("ld.shared.v4.u32 {%0,%1,%2,%3}, [%4];\n" : "=r"(v.x), "=r"(v.y), "=r"(v.z), "=r"(v.w) : "r"(a) : "memory");
  return v;
}
__device__ __forceinline__ void sts128(uint32_t a, uint32_t x, uint32_t y, uint32_t z, uint32_t w) {
  asm volatile("st.shared.v4.u32 [%0], {%1,%2,%3,%4};\n" ::"r"(a), "r"(x), "r"(y), "r"(z), "r"(w) : "memory");
}
__device__ __forceinline__ uint32_t pack_bf16(float lo, float hi) {
  uint32_t r;
  asm("cvt.rn.bf16x2.f32 %0, %1, %2;\n" : "=r"(r) : "f"(hi), "f"(lo));
  return r;
}
__device__ __forceinline__ uint32_t bmul2(uint32_t a, uint32_t b) {
  uint32_t r;
  asm("mul.rn.bf16x2 %0, %1, %2;\n" : "=r"(r) : "r"(a), "r"(b));
  return r;
}
__device__ __forceinline__ uint32_t bmax2(uint32_t a, uint32_t b) {
  uint32_t r;
  asm("max.bf16x2 %0, %1, %2;\n" : "=r"(r) : "r"(a), "r"(b));
  return r;
}
__device__ __forceinline__ uint32_t bfma2(uint32_t a, uint32_t b, uint32_t c) {
  uint32_t r;
  asm("fma.rn.bf16x2 %0, %1, %2, %3;\n" : "=r"(r) : "r"(a), "r"(b), "r"(c));
  return r;
}
__device__ __forceinline__ uint32_t badd2(uint32_t a, uint32_t b) {
  uint32_t r;
  asm("add.rn.bf16x2 %0, %1, %2;\n" : "=r"(r) : "r"(a), "r"(b));
  return r;
}
__device__ __forceinline__ void prefetch_l2(const void* p) { asm volatile("prefetch.global.L2 [%0];\n" ::"l"(p)); }
__device__ __forceinline__ void cp_async16n(uint32_t dst, const void* src) {
  asm volatile("cp.async.cg.shared.global [%0], [%1], 16;\n" ::"r"(dst), "l"(src) : "memory");
}
__device__ __forceinline__ void cp_async16(uint32_t dst, const void* src, uint32_t srcbytes) {
  asm volatile("cp.async.cg.shared.global.L2::256B [%0], [%1], 16, %2;\n" ::"r"(dst), "l"(src), "r"(srcbytes) : "memory");
}
__device__ __forceinline__ uint32_t ld_acquire(const uint32_t* p) {
  uint32_t v;
  asm volatile("ld.acquire.gpu.global.u32 %0, [%1];\n" : "=r"(v) : "l"(p) : "memory");
  return v;
}
__device__ __forceinline__ uint32_t ld_relaxed(const uint32_t* p) {
  uint32_t v;
  asm volatile("ld.relaxed.gpu.global.u32 %0, [%1];\n" : "=r"(v) : "l"(p) : "memory");
  return v;
}
__device__ __forceinline__ void st_release(uint32_t* p, uint32_t v) {
  asm volatile("st.release.gpu.global.u32 [%0], %1;\n" ::"l"(p), "r"(v) : "memory");
}
__device__ __forceinline__ void wait_flag(const uint32_t* p, uint32_t want) {
  int n = 0;
  while (ld_relaxed(p) != want && ++n < SPIN_LIMIT) __nanosleep(40);
  (void)ld_acquire(p);
}

struct Params {
  const __nv_bfloat16* x;
  const __nv_bfloat16* w;
  const __nv_bfloat16* q;
  const __nv_bfloat16* k;
  const __nv_bfloat16* v;
  const __nv_bfloat16* shift_k;
  const __nv_bfloat16* ssm_k;
  const __nv_bfloat16* ssm_D;
  const __nv_bfloat16* wo;
  __nv_bfloat16* out;
};

__device__ __forceinline__ uint32_t lds32(uint32_t a) {
  uint32_t v;
  asm volatile("ld.shared.u32 %0, [%1];\n" : "=r"(v) : "r"(a));
  return v;
}
#define W4(d, o) "=f"(d[o + 0]), "=f"(d[o + 1]), "=f"(d[o + 2]), "=f"(d[o + 3])
#define W8(d, o) W4(d, o), W4(d, o + 4)
#define W16(d, o) W8(d, o), W8(d, o + 8)
#define U4(c, d, o) c(d[o + 0]), c(d[o + 1]), c(d[o + 2]), c(d[o + 3])
#define U8(c, d, o) U4(c, d, o), U4(c, d, o + 4)
#define U16(c, d, o) U8(c, d, o), U8(c, d, o + 8)
#define U32(c, d, o) U16(c, d, o), U16(c, d, o + 16)
#define D32 "{%0,%1,%2,%3,%4,%5,%6,%7,%8,%9,%10,%11,%12,%13,%14,%15,%16,%17,%18,%19,%20,%21,%22,%23,%24,%25,%26,%27,%28,%29,%30,%31}"
#define D16 "{%0,%1,%2,%3,%4,%5,%6,%7,%8,%9,%10,%11,%12,%13,%14,%15}"
#define D8 "{%0,%1,%2,%3,%4,%5,%6,%7}"
template <int ACC> __device__ __forceinline__ void hmma_n128t(uint32_t (&d)[32], const uint32_t (&a)[4], uint64_t db) {
  if (ACC)
    asm volatile("wgmma.mma_async.sync.aligned.m64n128k16.f16.f16.f16 " D32 ", {%32,%33,%34,%35}, %36, 1, 1, 1, 1;\n"
                 : U32("+r", d, 0) : "r"(a[0]), "r"(a[1]), "r"(a[2]), "r"(a[3]), "l"(db));
  else
    asm volatile("wgmma.mma_async.sync.aligned.m64n128k16.f16.f16.f16 " D32 ", {%32,%33,%34,%35}, %36, 0, 1, 1, 1;\n"
                 : U32("=r", d, 0) : "r"(a[0]), "r"(a[1]), "r"(a[2]), "r"(a[3]), "l"(db));
}
template <int ACC, int TB> __device__ __forceinline__ void hmma_n32(uint32_t (&d)[8], const uint32_t (&a)[4], uint64_t db) {
  if (ACC)
    asm volatile("wgmma.mma_async.sync.aligned.m64n32k16.f16.f16.f16 " D8 ", {%8,%9,%10,%11}, %12, 1, 1, 1, %13;\n"
                 : U8("+r", d, 0) : "r"(a[0]), "r"(a[1]), "r"(a[2]), "r"(a[3]), "l"(db), "n"(TB));
  else
    asm volatile("wgmma.mma_async.sync.aligned.m64n32k16.f16.f16.f16 " D8 ", {%8,%9,%10,%11}, %12, 0, 1, 1, %13;\n"
                 : U8("=r", d, 0) : "r"(a[0]), "r"(a[1]), "r"(a[2]), "r"(a[3]), "l"(db), "n"(TB));
}
template <int ACC> __device__ __forceinline__ void hmma_n64t(uint32_t (&d)[16], const uint32_t (&a)[4], uint64_t db) {
  if (ACC)
    asm volatile("wgmma.mma_async.sync.aligned.m64n64k16.f16.f16.f16 " D16 ", {%16,%17,%18,%19}, %20, 1, 1, 1, 1;\n"
                 : U16("+r", d, 0) : "r"(a[0]), "r"(a[1]), "r"(a[2]), "r"(a[3]), "l"(db));
  else
    asm volatile("wgmma.mma_async.sync.aligned.m64n64k16.f16.f16.f16 " D16 ", {%16,%17,%18,%19}, %20, 0, 1, 1, 1;\n"
                 : U16("=r", d, 0) : "r"(a[0]), "r"(a[1]), "r"(a[2]), "r"(a[3]), "l"(db));
}
template <int N> __device__ __forceinline__ void fence_regs(uint32_t (&d)[N]) {
#pragma unroll
  for (int i = 0; i < N; i++) asm volatile("" : "+r"(d[i])::"memory");
}
__device__ __forceinline__ uint32_t hmul(uint32_t a, uint32_t b) { uint32_t r; asm("mul.rn.f16x2 %0, %1, %2;\n" : "=r"(r) : "r"(a), "r"(b)); return r; }
__device__ __forceinline__ uint32_t hadd(uint32_t a, uint32_t b) { uint32_t r; asm("add.rn.f16x2 %0, %1, %2;\n" : "=r"(r) : "r"(a), "r"(b)); return r; }
__device__ __forceinline__ uint32_t hsub(uint32_t a, uint32_t b) { uint32_t r; asm("sub.rn.f16x2 %0, %1, %2;\n" : "=r"(r) : "r"(a), "r"(b)); return r; }
__device__ __forceinline__ uint32_t hfma(uint32_t a, uint32_t b, uint32_t c) { uint32_t r; asm("fma.rn.f16x2 %0, %1, %2, %3;\n" : "=r"(r) : "r"(a), "r"(b), "r"(c)); return r; }
__device__ __forceinline__ uint32_t hfnma(uint32_t a, uint32_t b, uint32_t c) {
  uint32_t r;
  asm("{\n.reg .b32 t;\nneg.f16x2 t, %1;\nfma.rn.f16x2 %0, t, %2, %3;\n}\n" : "=r"(r) : "r"(a), "r"(b), "r"(c));
  return r;
}
__device__ __forceinline__ uint32_t hrefl(uint32_t p, uint32_t s) {
  uint32_t r;
  asm("{\n.reg .b32 t;\nneg.f16x2 t, %2;\nfma.rn.f16x2 %0, %1, %3, t;\n}\n" : "=r"(r) : "r"(p), "r"(s), "r"(0x40004000u));
  return r;
}
__device__ __forceinline__ void bfly(uint32_t xr, uint32_t xi, uint32_t tr, uint32_t ti, uint32_t yr, uint32_t yi, uint32_t ur,
                                     uint32_t ui, uint32_t& sr, uint32_t& si, uint32_t& dr, uint32_t& di) {
  const uint32_t pr = hfnma(xi, ti, hmul(xr, tr)), pi = hfma(xi, tr, hmul(xr, ti));
  sr = hfnma(yi, ui, hfma(yr, ur, pr));
  si = hfma(yi, ur, hfma(yr, ui, pi));
  dr = hrefl(pr, sr);
  di = hrefl(pi, si);
}
template <int BH> __device__ __forceinline__ void fft_e1(const uint32_t (&d)[32], const uint32_t (&tw)[16], uint32_t (&a2)[2][2][4]) {
#pragma unroll
  for (int be = 0; be < 2; be++)
#pragma unroll
    for (int s = 0; s < 2; s++) {
      const int o = 16 * s + 8 * be + 2 * BH, p = 2 * BH;
      bfly(d[o], d[o + 1], tw[p], tw[p + 1], d[o + 4], d[o + 5], tw[p + 4], tw[p + 5], a2[be][0][s], a2[be][0][2 + s],
           a2[be][1][s], a2[be][1][2 + s]);
    }
}
__device__ __forceinline__ uint32_t hfms(uint32_t a, uint32_t b, uint32_t c) {
  uint32_t r;
  asm("{\n.reg .b32 t;\nneg.f16x2 t, %3;\nfma.rn.f16x2 %0, %1, %2, t;\n}\n" : "=r"(r) : "r"(a), "r"(b), "r"(c));
  return r;
}
template <int C, int J> __device__ __forceinline__ void fft_e2(const uint32_t (&d0)[8], const uint32_t (&d1)[8], uint32_t (&a3)[2][4]) {
  const uint32_t ur = d0[2 * J], ui = d0[4 + 2 * J], hr = d0[2 * J + 1], hi = d0[5 + 2 * J];
  const uint32_t vr = d1[2 * J], vi = d1[4 + 2 * J], gr = d1[2 * J + 1], gi = d1[5 + 2 * J];
  const uint32_t pr = hfnma(ui, hi, hmul(ur, hr)), pi = hfma(ui, hr, hmul(ur, hi));
  a3[0][2 + C] = pr;
  a3[0][C] = pi;
  a3[1][2 + C] = hfnma(vi, hi, hfma(vr, hr, hfnma(ui, gi, hfms(ur, gr, pi))));
  a3[1][C] = hfma(vi, hr, hfma(vr, hi, hfma(ui, gr, hfma(ur, gi, pr))));
}
__device__ __forceinline__ void fft_e3(const uint32_t (&d)[2][8], const uint32_t (&tw)[16], uint32_t zaddr) {
#pragma unroll
  for (int rho = 0; rho < 2; rho++) {
    uint32_t zr[4], zi[4];
#pragma unroll
    for (int nb = 0; nb < 4; nb++) {
      const uint32_t xi = d[nb >> 1][2 * (nb & 1) + rho], xr = d[nb >> 1][4 + 2 * (nb & 1) + rho];
      const uint32_t tr = tw[8 + 4 * rho + 2 * (nb & 1)], ti = tw[9 + 4 * rho + 2 * (nb & 1)];
      zr[nb] = hfnma(xi, ti, hmul(xr, tr));
      zi[nb] = hfma(xi, tr, hmul(xr, ti));
    }
    stsm4(zaddr + rho * 2048, zr[0], zr[1], zr[2], zr[3]);
    stsm4(zaddr + rho * 2048 + 1024, zi[0], zi[1], zi[2], zi[3]);
  }
}
__device__ __forceinline__ float bf_lo(uint32_t v) {
  uint32_t r;
  asm("prmt.b32 %0, %1, 0, 0x1044;\n" : "=r"(r) : "r"(v));
  return __uint_as_float(r);
}
__device__ __forceinline__ float bf_hi(uint32_t v) { return __uint_as_float(v & 0xffff0000u); }
__device__ __forceinline__ float ex2(float x) {
  float r;
  asm("ex2.approx.ftz.f32 %0, %1;\n" : "=f"(r) : "f"(x));
  return r;
}
__device__ __forceinline__ float rcp(float x) {
  float r;
  asm("rcp.approx.ftz.f32 %0, %1;\n" : "=f"(r) : "f"(x));
  return r;
}

__device__ __forceinline__ int g2_a(int s) { return ((0xA1054 >> (4 * s)) & 15) * 16384; }
__device__ __forceinline__ int g2_b(int s) { return ((0xCDB32 >> (4 * s)) & 15) * 16384; }
static_assert(OFF_U == 10 * 16384 && OFF_H == 12 * 16384 && OFF_OP == 4 * 16384, "units");
__device__ __forceinline__ int g2_k(int hp, int i) {
  return i < 2 ? hp ^ 1 ^ i : i < 4 ? (hp & ~1) ^ i : ((hp & ~3) + i) & 15; }
__device__ __forceinline__ int y_slot(int wg, int it) {
  static_assert(T_B2 == T_TW + 8192 && T_A1 == T_B2 + 4096, "y slots");
  return OFF_T + T_TW + ((it + 3) & 3) * 4096 + wg * 2048;
}

__device__ __forceinline__ void to_arr(uint32_t (&d)[4], uint4 v) { d[0] = v.x; d[1] = v.y; d[2] = v.z; d[3] = v.w; }

__device__ __forceinline__ void attn_stage(uint32_t sb, int blk, int lane, const float (&acc)[96], uint32_t (&k1)[2][4]) {
  const int lr = lane & 7, lm = lane >> 3;
  const uint32_t base = sb + OFF_VP + (blk * 16 + lr + 8 * (lm & 1)) * 128;
#pragma unroll
  for (int i = 0; i < 8; i++) k1[i >> 2][i & 3] = pack_bf16(acc[34 + 4 * i], acc[35 + 4 * i]);
  const uint32_t kh = sb + OFF_KH + blk * 2048 + lane * 16;
  sts128(kh, k1[0][0], k1[0][1], k1[0][2], k1[0][3]);
  sts128(kh + 512, k1[1][0], k1[1][1], k1[1][2], k1[1][3]);
#pragma unroll
  for (int j = 0; j < 8; j += 2)
    stsm4(base + (((j + (lm >> 1)) ^ lr) << 4), pack_bf16(acc[64 + 4 * j], acc[65 + 4 * j]),
          pack_bf16(acc[66 + 4 * j], acc[67 + 4 * j]), pack_bf16(acc[68 + 4 * j], acc[69 + 4 * j]),
          pack_bf16(acc[70 + 4 * j], acc[71 + 4 * j]));
}
__device__ __forceinline__ void attn_pack(const float (&acc)[96], uint32_t (&qa)[2][8], uint32_t (&k0)[2][4]) {
#pragma unroll
  for (int hd = 0; hd < 2; hd++) {
#pragma unroll
    for (int i = 0; i < 8; i++) {
      asm volatile("cvt.rn.bf16x2.f32 %0, %1, %2;\n" : "=r"(qa[hd][i]) : "f"(acc[16 * hd + 2 * i + 1]), "f"(acc[16 * hd + 2 * i]));
    }
#pragma unroll
    for (int i = 0; i < 4; i++) {
      asm volatile("cvt.rn.bf16x2.f32 %0, %1, %2;\n" : "=r"(k0[hd][i]) : "f"(acc[33 + 16 * hd + 4 * i]), "f"(acc[32 + 16 * hd + 4 * i]));
    }
  }
}
__device__ __forceinline__ void attn_own(const uint32_t (&k0)[2][4], const uint32_t (&k1)[2][4], bool le0, bool le1,
                                         const uint32_t (&qa)[2][8], float (&l)[2][4]) {
#pragma unroll
  for (int hd = 0; hd < 2; hd++) {
    float s0[4], s1[4];
    mma16816_z(s0, qa[hd][0], qa[hd][1], qa[hd][2], qa[hd][3], k0[hd][0], k0[hd][1]);
    mma16816_z(s1, qa[hd][0], qa[hd][1], qa[hd][2], qa[hd][3], k1[hd][0], k1[hd][1]);
    mma16816(s0, qa[hd][4], qa[hd][5], qa[hd][6], qa[hd][7], k0[hd][2], k0[hd][3]);
    mma16816(s1, qa[hd][4], qa[hd][5], qa[hd][6], qa[hd][7], k1[hd][2], k1[hd][3]);
    l[hd][0] = s0[0];
    l[hd][1] = s0[1];
    l[hd][2] = le0 ? s1[2] : s0[2];
    l[hd][3] = le1 ? s1[3] : s0[3];
  }
}
template <int N> __device__ __forceinline__ void quad_softmax(float (&x)[N][2], uint32_t (&pp)[N]) {
  const float c2 = 1.4426950408889634f;
  uint32_t q[N], mx[N / 2];
#pragma unroll
  for (int n = 0; n < N; n++) {
    const uint32_t r = pack_bf16(x[n][0], x[n][1]);
    q[n] = bfma2(r, 0x3e353e35u, bmul2(r, 0x379e379eu));
    x[n][0] = bf_lo(q[n]);
    x[n][1] = bf_hi(q[n]);
  }
#pragma unroll
  for (int n = 0; n < N / 2; n++)
    mx[n] = bmax2(__byte_perm(q[2 * n], q[2 * n + 1], 0x5410), __byte_perm(q[2 * n], q[2 * n + 1], 0x7632));
#pragma unroll
  for (int o = 1; o <= 2; o++)
#pragma unroll
    for (int n = 0; n < N / 2; n++) mx[n] = bmax2(mx[n], __shfl_xor_sync(0xffffffffu, mx[n], o));
  float m[N], t[N];
#pragma unroll
  for (int n = 0; n < N / 2; n++) {
    m[2 * n] = bf_lo(mx[n]);
    m[2 * n + 1] = bf_hi(mx[n]);
  }
#pragma unroll
  for (int n = 0; n < N; n++) {
    const float nm = -m[n] * c2;
    x[n][0] = ex2(fmaf(x[n][0], c2, nm));
    x[n][1] = ex2(fmaf(x[n][1], c2, nm));
    t[n] = x[n][0] + x[n][1];
  }
#pragma unroll
  for (int o = 1; o <= 2; o++)
#pragma unroll
    for (int n = 0; n < N; n++) t[n] += __shfl_xor_sync(0xffffffffu, t[n], o);
#pragma unroll
  for (int n = 0; n < N; n++) {
    const float inv = rcp(t[n]);
    pp[n] = pack_bf16(x[n][0] * inv, x[n][1] * inv);
  }
}
__device__ __forceinline__ void attn_pv(uint32_t dst, const uint32_t (&va)[4], const uint32_t (&vb)[4], uint32_t pp,
                                        uint32_t maskLE) {
  const uint32_t b0 = pp & ~maskLE, b1 = pp & maskLE;
  float oa[4], ob[4];
  mma16816_z(oa, va[0], va[1], va[2], va[3], b0, b1);
  mma16816_z(ob, vb[0], vb[1], vb[2], vb[3], b0, b1);
  stsm4t(dst, pack_bf16(oa[0], oa[1]), pack_bf16(oa[2], oa[3]), pack_bf16(ob[0], ob[1]), pack_bf16(ob[2], ob[3]));
}

template <int MODE>
__global__ void __cluster_dims__(2, 1, 1) __launch_bounds__(NTHREADS, 1)
fused_kernel(const Params p, const __grid_constant__ CUtensorMap tmX, const __grid_constant__ CUtensorMap tmW,
             const __grid_constant__ CUtensorMap tmWo,
             const __grid_constant__ CUtensorMap tmQ, const __grid_constant__ CUtensorMap tmO,
             const __grid_constant__ CUtensorMap tmXh, const __grid_constant__ CUtensorMap tmWh) {
  extern __shared__ __align__(1024) uint8_t smem[];
  const uint32_t sb = smem_u32(smem) - OFF_L0;
  const uint32_t bars = sb + OFF_BAR;
  const int tid = threadIdx.x, lane = tid & 31, warp = __shfl_sync(0xffffffffu, tid >> 5, 0);
  const int rank = blockIdx.x & 1;
  const bool halo_cta = blockIdx.x < 4;
  if (halo_cta && MODE != 0) return;
  int grp, mem;
  {
    const int t = (blockIdx.x >> 1) - 4, u = t - 32;
    const int q7 = (u * 37) >> 8;
    const bool lo = (unsigned)t < 32u, mid = (unsigned)u < 28u;
    grp = lo ? (t & 7) : (mid ? 1 + u - 7 * q7 : 0);
    mem = lo ? (t >> 3) : (mid ? 4 + q7 : (t < 0 ? t + 6 : t - 54));
  }
  const int rg = (grp >> 2) * 4 + (mem >> 1), hp = (grp & 3) * 4 + (mem & 1) * 2 + rank;
  const int rb2 = (grp >> 2) * 8 + mem, cb2 = (grp & 3) * 2 + rank;
  const int chb = grp * 16 + mem * 2 + rank;
  const int cta = rg * 16 + hp;
  const int par = rg >> 2, gidx = rg & 3;

  if (tid < 256 && !halo_cta && MODE != 2) {
    const int r = tid >> 3, c = tid & 7;
    const uint32_t so = r * 128 + ((c ^ (r & 7)) << 4);
    const __nv_bfloat16* wg0 = p.w + (size_t)r * (3 * DM) + hp * 64 + c * 8;
    const __nv_bfloat16* xg0 = p.x + (size_t)(2 * (gidx * 256 + r) + par) * DM + c * 8;
#pragma unroll
    for (int j = 0; j < 3; j++) cp_async16n(sb + OFF_1B + j * 4096 + so, wg0 + j * DM);
#pragma unroll
    for (int i = 0; i < 8; i++) cp_async16n(sb + i * 4096 + so, xg0 + (size_t)i * 64 * DM);
    asm volatile("cp.async.commit_group;\n" ::: "memory");
  }
  if (tid == 256) {
    prefetch_tmap(halo_cta ? &tmXh : &tmX);
#pragma unroll
    for (int i = 0; i < NS1B; i++) mbar_init(bars + 8 * (BAR_FULLB + i), 1);
#pragma unroll
    for (int i = 0; i < NS1A; i++) mbar_init(bars + 8 * (BAR_FULLA + i), 1);
    asm volatile("fence.mbarrier_init.release.cluster;\n" ::: "memory");
    if (!halo_cta && MODE != 2) {
      mbar_expect_tx(bars + 8 * (BAR_FULLB + 1), STG1B);
      tma_load_3d(sb + OFF_1B + 1 * STG1B, &tmW, bars + 8 * (BAR_FULLB + 1), hp * 64, 32, 0);
      mbar_expect_tx(bars + 8 * (BAR_FULLB + 2), STG1B);
      tma_load_3d(sb + OFF_1B + 2 * STG1B, &tmW, bars + 8 * (BAR_FULLB + 2), hp * 64, 64, 0);
    } else {
      prefetch_tmap(&tmWh);
    }
  } else if (tid == 288) {
#pragma unroll
    for (int i = 0; i < NS1A; i++) mbar_init(bars + 8 * (BAR_EMPTYA + i), 4);
#pragma unroll
    for (int i = 0; i < NS1B; i++) mbar_init(bars + 8 * (BAR_EMPTYB + i), 2);
    asm volatile("fence.mbarrier_init.release.cluster;\n" ::: "memory");
  } else if (tid == 320) {
#pragma unroll
    for (int i = 0; i < NS2; i++) {
      mbar_init(bars + 8 * (BAR_FULL2 + i), 1);
      mbar_init(bars + 8 * (BAR_EMPTY2 + i), 4);
    }
    mbar_init(bars + 8 * BAR_DEAD, 2);
    mbar_init(bars + 8 * (BAR_DEAD + 1), 2);
    mbar_init(bars + 8 * BAR_X, 2);
    mbar_init(bars + 8 * BAR_REL, 2);
    asm volatile("fence.mbarrier_init.release.cluster;\n" ::: "memory");
  } else if (tid == 352) {
    mbar_init(bars + 8 * BAR_T, 1);
    mbar_init(bars + 8 * BAR_UH, 3);
    mbar_init(bars + 8 * BAR_LFREE, 4);
    mbar_init(bars + 8 * BAR_LAND, 1);
    mbar_init(bars + 8 * BAR_U, 1);
    mbar_init(bars + 8 * BAR_Q, 1);
    mbar_init(bars + 8 * BAR_STG, 9);
    asm volatile("fence.mbarrier_init.release.cluster;\n" ::: "memory");
  }
  if (warp == 8) PROF2(23);
  cluster_sync_all();
  if (warp == 8) PROF2(24);

  if (warp >= 8) {
    const int hw = warp - 8;
    const int lr = lane & 7, lm = lane >> 3;
    auto g1_issue_a = [&](int j, int s) {
      const uint32_t fb = bars + 8 * (BAR_FULLA + s);
      mbar_expect_tx(fb, STG1A);
      tma_load_3d_mc(sb + s * STG1A + rank * 16384, &tmX, fb, j * 64, par, gidx * 256 + rank * 128);
    };
    auto g1_issue_b = [&](int kb, int s) {
      const uint32_t fb = bars + 8 * (BAR_FULLB + s);
      mbar_expect_tx(fb, STG1B);
      tma_load_3d(sb + OFF_1B + s * STG1B, &tmW, fb, hp * 64, kb * 32, 0);
    };
    asm volatile("setmaxnreg.dec.sync.aligned.u32 %0;\n" :: "n"(REG_HELP));

    if (halo_cta) {
      if (hw == 0) {
        int s = 0, ph = 1;
#pragma unroll 1
        for (int kb = 0; kb < 16; kb++) {
          mbar_wait(bars + 8 * (BAR_EMPTYB + s), ph);
          const uint32_t fb = bars + 8 * (BAR_FULLB + s), st = sb + s * STGH;
          if (elect_one()) {
            mbar_expect_tx(fb, STGH);
            tma_load_4d(st, &tmXh, fb, kb * 64, 248, 0, 0);
            tma_load_3d(st + 8192, &tmWh, fb, 0, kb * 64, 16 + blockIdx.x * 4);
            tma_load_3d(st + 8192 + 32768, &tmWh, fb, 0, kb * 64, 32 + blockIdx.x * 4);
          }
          if (++s == 3) { s = 0; ph ^= 1; }
        }
      }
      __syncwarp();
    } else if (hw == 0) {
      uint32_t epoch = 0;
      if (lane < (MODE == 2 ? NS2 : 2)) mbar_arrive_cluster_n(mapa(bars, rank) + 8 * (BAR_EMPTY2 + lane), 4);
      if (MODE != 2) {
      epoch = ld_relaxed(g_flag_o + 2 * cta) + 1;
      if (lane == 0) {
        mbar_expect_tx(bars + 8 * BAR_U, 32768);
        mbar_expect_tx(bars + 8 * BAR_LAND, 32768 + 64);
        mbar_expect_tx(bars + 8 * BAR_Q, 32768);
        mbar_expect_tx(bars + 8 * BAR_T, T_END);
      }
      {
        int sa = 1, pha = 1, sbb = 2, phb = 1;
#pragma unroll 1
        for (int kb = 2; kb < 32; kb++) {
          if (!(kb & 1)) {
            mbar_wait(bars + 8 * (BAR_EMPTYA + sa), pha);
            if (elect_one()) g1_issue_a(kb >> 1, sa);
            if (++sa == NS1A) { sa = 0; pha ^= 1; }
          }
          mbar_wait(bars + 8 * (BAR_EMPTYB + sbb), phb);
          if (kb > 2 && elect_one()) g1_issue_b(kb, sbb);
          __syncwarp();
          if (kb >= PF0 && kb < PF0 + 12)
            prefetch_l2((kb < PF0 + 8 ? p.q + (size_t)chb * 16384 + (kb - PF0) * 2048 : p.wo + (size_t)chb * 8192 + (kb - PF0 - 8) * 2048) + lane * 64);
          if (kb == 4) PROF2(27);
          if (kb == 1) PROF2(38);
          if (kb == 2) PROF2(39);
          if (++sbb == NS1B) { sbb = 0; phb ^= 1; }
        }
      }
      static_assert(32 % NS1B == 2 && (32 / NS1B) % 2 == 0 && OFF_Q == OFF_1B && 2 * STG1B == 6 * 4096, "slots / parity of these loads");
      const uint8_t* tab = reinterpret_cast<const uint8_t*>(g_tab);
      if (lane == 0) {
        prefetch_tmap(&tmWo);
        prefetch_tmap(&tmQ);
        prefetch_tmap(&tmO);
        bulk_load(sb + OFF_T + T_A1, tab + T_A1, T_END - T_A1, bars + 8 * BAR_T);
        mbar_wait(bars + 8 * (BAR_EMPTYB + 2), 1);
        tma_load_5d(sb + OFF_Q + 6 * 4096, &tmQ, bars + 8 * BAR_Q, (chb & ~1) * 8, rank * 32 + 24);
        tma_load_5d(sb + OFF_Q + 7 * 4096, &tmQ, bars + 8 * BAR_Q, (chb & ~1) * 8, rank * 32 + 28);
        if (gidx != 0) wait_flag(g_flag_h + (hp >> 2), epoch);
      }
      __syncwarp();
      {
        uint4 hk0 = make_uint4(0, 0, 0, 0), hk1 = hk0, hv0 = hk0, hv1 = hk0;
        if (gidx != 0) {
          const uint4* src = g_halo + cta * 128 + lane;
          hk0 = __ldcg(src); hk1 = __ldcg(src + 32); hv0 = __ldcg(src + 64); hv1 = __ldcg(src + 96);
        }
        if (lane == 0) {
          mbar_wait(bars + 8 * (BAR_EMPTYB + 3), 1);
          bulk_load(sb + OFF_T, tab, T_TW, bars + 8 * BAR_T);
        }
        __syncwarp();
        PROF2(18);
        sts128(sb + OFF_L0 + lane * 16, hk0.x, hk0.y, hk0.z, hk0.w);
        sts128(sb + OFF_L0 + 512 + lane * 16, hk1.x, hk1.y, hk1.z, hk1.w);
        stsm4(sb + OFF_L0 + 1024 + lr * 128 + ((lm ^ lr) << 4), hv0.x, hv0.y, hv0.z, hv0.w);
        stsm4(sb + OFF_L0 + 1024 + lr * 128 + (((4 + lm) ^ lr) << 4), hv1.x, hv1.y, hv1.z, hv1.w);
        __syncwarp();
        if (lane == 0) {
          mbar_arrive(bars + 8 * BAR_STG);
          mbar_wait(bars + 8 * (BAR_EMPTYB + 4), 1);
          bulk_load(sb + OFF_T + T_TW, tab + T_TW, T_A1 - T_TW, bars + 8 * BAR_T);
          mbar_wait(bars + 8 * BAR_EMPTYB, 0);
#pragma unroll 1
          for (int i = 0; i < 6; i++) tma_load_5d(sb + OFF_Q + i * 4096, &tmQ, bars + 8 * BAR_Q, (chb & ~1) * 8, rank * 32 + i * 4);
        }
        __syncwarp();
      }
      }
      if (MODE != 1) {
        auto korder = [&](int i) { return MODE == 2 ? i : g2_k(hp, i); };
        const __nv_bfloat16* osrc = g_o + (size_t)(rb2 >> 1) * 16 * 16384 + ((rb2 & 1) * 2 + rank) * 4096;
        const uint32_t* flag = g_flag_o + ((rb2 >> 1) * 32 + korder(lane & 15) * 2 + (rb2 & 1));
        uint32_t ready = MODE == 0 ? 0u : ~0u, pv = 0;
        auto look = [&]() {
          ready |= __ballot_sync(0xffffffffu, pv == epoch);
          asm volatile("fence.acquire.gpu;\n" ::: "memory");
          fence_async_all();
        };
        const __nv_bfloat16* o23[2] = {osrc + korder(2) * 16384, osrc + korder(3) * 16384};
        if (MODE == 0) {
          asm volatile("" : "+l"(o23[0]), "+l"(o23[1]), "+l"(flag));
          if (lane < 4 && lane != 1) mbar_expect_tx(bars + 8 * (BAR_FULL2 + lane), STG2);
          mbar_wait_idle(bars + 8 * (BAR_EMPTY2 + 2), 0);
          mbar_wait(bars + 8 * (BAR_EMPTY2 + 3), 0);
          mbar_wait_idle(bars + 8 * BAR_REL, 0);
          if (elect_one()) {
            tma_load_3d(sb + g2_b(0), &tmWo, bars + 8 * BAR_FULL2, 0, korder(0) * 64, cb2 * 2);
            tma_load_3d(sb + g2_b(1), &tmWo, bars + 8 * (BAR_FULL2 + 1), 0, korder(1) * 64, cb2 * 2);
          }
        }
#pragma unroll
        for (int i = MODE == 0 ? 2 : 0; i < 16; i++) {
          const int kb = korder(i), s = i % NS2, ph = (i / NS2) & 1;
          const uint32_t fb = bars + 8 * (BAR_FULL2 + s);
          if (!((ready >> i) & 1)) {
            int n = 0;
            do {
              ready |= __ballot_sync(0xffffffffu, ld_acquire(flag) == epoch);
            } while (!((ready >> i) & 1) && ++n < SPIN_LIMIT);
            fence_async_all();
          }
          if (i == 2) PROF(21);
          const bool pre = MODE == 0 && i < 4;
          if (!pre) mbar_wait(bars + 8 * (BAR_EMPTY2 + s), ph);
          if (elect_one()) {
            if (!pre) mbar_expect_tx(fb, STG2);
            asm volatile(
                "cp.async.bulk.shared::cluster.global.mbarrier::complete_tx::bytes.multicast::cluster [%0], [%1], %2, [%3], %4;\n"
                ::"r"(sb + g2_a(s) + rank * 8192), "l"(pre ? o23[i & 1] : osrc + kb * 16384), "r"(8192), "r"(fb), "h"((uint16_t)3) : "memory");
            if (!pre) tma_load_3d(sb + g2_b(s), &tmWo, fb, 0, kb * 64, cb2 * 2);
          }
          if (MODE == 0 && i == LA0) pv = ld_relaxed(flag);
          if (MODE == 0 && i == LA1) look();
          if (i == 3) PROF(37);

        }
      }
      __syncwarp();
    } else if (MODE != 2) {
      {
        const int g = lane >> 2, t = lane & 3;
        uint32_t w[2][4];
#pragma unroll
        for (int h = 0; h < 2; h++) {
          const uint2 x = __ldg(reinterpret_cast<const uint2*>(p.shift_k + ((chb & ~1) * 8 + h * 8 + g) * 4));
          w[h][0] = __byte_perm(x.x, x.x, 0x1010);
          w[h][1] = __byte_perm(x.x, x.x, 0x3232);
          w[h][2] = __byte_perm(x.y, x.y, 0x1010);
          w[h][3] = __byte_perm(x.y, x.y, 0x3232);
        }
        auto swz = [](int r) { return (((r & 29) | ((r ^ (r >> 2)) & 2)) << 5) | (r & 16); };
        const uint32_t kring = sb + OFF_H + (hw - 1) * 8192, vring = kring + 4096;
        const int s0 = rank * 32 + (hw - 1) * 11, s1 = hw == 3 ? rank * 32 + 32 : s0 + 11;
        const size_t goff = (size_t)(lane >> 1) * DM + (chb & ~1) * 8 + (lane & 1) * 8;
        const __nv_bfloat16* kg = p.k + goff;
        const __nv_bfloat16* vg = p.v + goff;
        const uint32_t d0 = swz(lane >> 1) ^ ((lane & 1) << 4), d1 = swz(16 + (lane >> 1)) ^ ((lane & 1) << 4);
        auto issue = [&](int st) {
          const uint32_t so = (st & 3) << 10;
          cp_async16(kring + so + d0, kg + (size_t)st * 32 * DM, 16);
          cp_async16(kring + so + d1, kg + (size_t)(st * 32 + 16) * DM, 16);
          cp_async16(vring + so + d0, vg + (size_t)st * 32 * DM, 16);
          cp_async16(vring + so + d1, vg + (size_t)(st * 32 + 16) * DM, 16);
        };
        const int xa = 8 * (lr >> 1) + 2 * lm + (lr & 1), xb = 8 * (lr >> 1) - 4 + 2 * (lm & 1) + (lr & 1);
        const uint32_t la = swz(xa), lb = swz(xb & 31);
        const int backb = xb < 0 ? 1 : 0;
        const uint32_t ud[2] = {mapa(sb + OFF_U + g * 4096 + t * 16, 0), mapa(sb + OFF_U + g * 4096 + t * 16, 1)};
        const uint32_t ub[2] = {mapa(bars + 8 * BAR_U, 0), mapa(bars + 8 * BAR_U, 1)};
        if (lane == 0) mbar_wait(bars + 8 * (BAR_FULLB + NS1B - 1), 0);
        __syncwarp();
        if (lane >= 24) cp_async16(kring + (((s0 - 1) & 3) << 10) + d1, s0 > 0 ? kg + (size_t)(s0 * 32 - 16) * DM : kg, s0 > 0 ? 16 : 0);
        issue(s0);
        asm volatile("cp.async.commit_group;\n" ::: "memory");
        issue(s0 + 1);
        asm volatile("cp.async.commit_group;\n" ::: "memory");
#pragma unroll 1
        for (int st = s0; st < s1; st++) {
          if (st + 2 < s1) issue(st + 2);
          if (hw == 1 && st - s0 < 8) prefetch_l2(p.ssm_k + (size_t)(chb * 8 + st - s0) * SEQ + lane * 64);
          if (hw == 2 && st == s0 + 4 && lane < 2) prefetch_l2(g_tab + (chb * 2 + lane) * 32);
          const uint32_t uo = (st ^ ((g ^ (st >> 2)) & 1)) * 64;
          asm volatile("cp.async.commit_group;\n" ::: "memory");
          asm volatile("cp.async.wait_group 2;\n" ::: "memory");
          __syncwarp();
#pragma unroll
          for (int h = 0; h < 2; h++) {
            uint32_t e[6], vv[4], e4[4];
            ldsm4t(e4, kring + ((st & 3) << 10) + (la ^ (h << 4)));
            ldsm2t(e[0], e[1], kring + (((st - backb) & 3) << 10) + (lb ^ (h << 4)));
            ldsm4t(vv, vring + ((st & 3) << 10) + (la ^ (h << 4)));
            e[2] = e4[0]; e[3] = e4[1]; e[4] = e4[2]; e[5] = e4[3];
            uint32_t o[5];
#pragma unroll
            for (int i = 0; i < 5; i++) o[i] = __byte_perm(e[i], e[i + 1], 0x5432);
#pragma unroll
            for (int i = 0; i < 4; i++) {
              uint32_t a = bmul2(o[i], w[h][3]);
              a = bfma2(e[i + 1], w[h][2], a);
              a = bfma2(o[i + 1], w[h][1], a);
              a = bfma2(e[i + 2], w[h][0], a);
              vv[i] = bmul2(a, vv[i]);
            }
            st_async128(ud[h] + uo, ub[h], vv[0], vv[1], vv[2], vv[3]);
          }
          __syncwarp();
        }
        PROF(16);
      }
      {
        const int rw = (lane >> 3) + (lane & 4), ck = lane & 3;
        const uint32_t so = rw * 64 + ck * 16, dof = rw * 128 + ((ck ^ rw) << 4);
        const uint8_t* hsrc = reinterpret_cast<const uint8_t*>(p.ssm_k + (size_t)chb * 8 * SEQ) + so;
        const float dv = lane < 8 ? __bfloat162float(p.ssm_D[chb * 8 + lane]) : 0.f;
        uint32_t x[32];
        auto load = [&](const uint8_t* src, int i) {
          asm volatile("ld.v4.u32 {%0,%1,%2,%3}, [%4];\n" : "=r"(x[4 * i]), "=r"(x[4 * i + 1]), "=r"(x[4 * i + 2]), "=r"(x[4 * i + 3])
                       : "l"(src + i * 512) : "memory");
        };
#pragma unroll
        for (int i = 0; i < 8; i++) load(hsrc + (hw - 1) * 4096, i);
        nb_sync(NB_HELP3, 96);
        mbar_wait(bars + 8 * BAR_U, 0);
        int eh = 0;
#pragma unroll 1
        for (int n = 2 * (hw - 1); n < 16; n += (n & 1) ? 5 : 1) {
          const int c = n >> 1;
          const uint8_t* nsrc = (n & 1) ? hsrc + (c < 5 ? c + 3 : c) * 4096
                                        : smem - OFF_L0 + OFF_U + c * 4096 + (so ^ (((c ^ (lane >> 2)) & 1) << 6));
          const uint32_t dst = sb + ((n & 1) ? OFF_U : OFF_H) + c * 4096 + dof;
          const float dc = __shfl_sync(0xffffffffu, dv, c);
          const float h0 = bf_lo(x[0]) + ((lane | (n & 1)) == 0 ? dc : 0.f), h1 = bf_hi(x[0]);
          x[0] = pack_bf16(h0, h1);
          uint32_t m[2] = {x[0], x[1]};
#pragma unroll
          for (int i = 2; i < 32; i++) asm("max.xorsign.abs.bf16x2 %0, %0, %1;\n" : "+r"(m[i & 1]) : "r"(x[i]));
          asm("max.xorsign.abs.bf16x2 %0, %0, %1;\n" : "+r"(m[0]) : "r"(m[1]));
          const uint32_t e = max(__reduce_max_sync(0xffffffffu, max((m[0] >> 7) & 255u, (m[0] >> 23) & 255u)), 5u);
          const uint32_t sc = (259u - e) * 0x00800080u;
#pragma unroll
          for (int i = 0; i < 8; i++) {
            uint32_t o[4];
#pragma unroll
            for (int j = 0; j < 4; j++) {
              const uint32_t v = bmul2(x[4 * i + j], sc);
              asm("cvt.rn.f16x2.f32 %0, %1, %2;\n" : "=r"(o[j]) : "f"(bf_hi(v)), "f"(i + j == 0 ? h0 * bf_hi(sc) : bf_lo(v)));
            }
            sts128((dst + (i & 3) * 1024) ^ ((i >> 2) << 6), o[0], o[1], o[2], o[3]);
            load(nsrc, i);
          }
          if (n & 1) {
            const int f = min(max((int)e + eh - 129, 0), 254);
            if (lane < 2)
              asm volatile("st.async.weak.shared::cluster.mbarrier::complete_tx::bytes.b32 [%0], %2, [%1];\n"
                           ::"r"(mapa(sb + OFF_SC + rank * 32 + c * 4, lane)), "r"(mapa(bars + 8 * BAR_LAND, lane)), "r"(f << 7) : "memory");
          }
          eh = e;
        }
        fence_async_smem();
        __syncwarp();
        if (lane == 0) mbar_arrive(bars + 8 * BAR_UH);
        PROF(32);
      }
      if (hw < 3) {
        const uint32_t rb = mapa(bars, lane & 1);
        const uint32_t epoch = ld_relaxed(g_flag_o + (2 * cta + hw - 1)) + 1;
        const bool own = hw - 1 == (rb2 & 1);
        nb_sync(NB_OREADY + hw - 1, 160);
        if (lane == 0) {
          asm volatile("cp.async.bulk.global.shared::cta.bulk_group [%0], [%1], %2;\n" ::"l"(g_o + (size_t)cta * 16384 + (hw - 1) * 8192),
                       "r"(sb + OFF_OP + (own ? 16384 : 0)), "r"(16384) : "memory");
          bulk_commit();
        }
        if (lane < 2) {
          mbar_arrive_cluster(rb + 8 * (BAR_EMPTY2 + 2));
          mbar_arrive_cluster(rb + 8 * (BAR_EMPTY2 + 3));
        }
        if (lane == 0) {
          bulk_wait0();
          if (own) mbar_expect_tx(bars + 8 * (BAR_FULL2 + 1), 16384);
          mbar_arrive_cluster(mapa(bars, own ? rank : rank ^ 1) + 8 * BAR_X);
          st_release(g_flag_o + (2 * cta + hw - 1), epoch);
          mbar_arrive(bars + 8 * BAR_REL);
        }
        __syncwarp();
        PROF(own ? 17 : 19);
      } else {
        if (MODE == 0) {
          mbar_wait_idle(bars + 8 * BAR_X, 0);
          if (elect_one())
            asm volatile("cp.async.bulk.shared::cluster.shared::cta.mbarrier::complete_tx::bytes [%0], [%1], %2, [%3];\n"
                         ::"r"(mapa(sb + OFF_OP, rank ^ 1)), "r"(sb + OFF_OP + 16384), "r"(16384),
                         "r"(mapa(bars + 8 * BAR_FULL2, rank ^ 1)) : "memory");
        }
        if (MODE == 0) {
          mbar_wait_idle(bars + 8 * BAR_DEAD, 0);
          if (elect_one()) {
            tma_load_3d(sb + g2_b(2), &tmWo, bars + 8 * (BAR_FULL2 + 2), 0, g2_k(hp, 2) * 64, cb2 * 2);
            tma_load_3d(sb + g2_b(3), &tmWo, bars + 8 * (BAR_FULL2 + 3), 0, g2_k(hp, 3) * 64, cb2 * 2);
          }
        }
        __syncwarp();
      }
    }
    if (!halo_cta && MODE != 2 && (F4 || hw)) {
      {
        const int c8 = (4 * (lr >> 1) + 2 * (lm & 1) + (lr & 1)) & 7;
        const bool own = (lr >> 2) == rank;
        const uint32_t ya = sb + (own ? y_slot(c8 & 1, c8 >> 1) : OFF_LAND + c8 * 2048);
        const uint32_t yx = ((lm >> 1) ^ lr) << 4;
        const int row = (lane >> 4) * 8 + ((lane >> 3) & 1) * 16 + ((lane >> 2) & 1);
        uint2* og = reinterpret_cast<uint2*>(p.out + (size_t)(rank * 1024 + row) * (2 * DM) + (chb & ~1) * 8 + (lane & 3) * 4);
        const uint32_t qa = sb + OFF_Q + (lane >> 4) * 512 + (lane & 15) * 8;
        mbar_wait(bars + 8 * BAR_Q, 0);
        mbar_wait_idle(bars + 8 * BAR_LAND, 0);
        PROF(33);
        const uint32_t t0 = clock();
        const uint4 s4 = lds128(sb + OFF_SC + (lane & 3) * 16);
        const uint32_t sc[2] = {s4.x | (s4.y << 16), s4.z | (s4.w << 16)};
        auto fin = [&](uint32_t q2, uint32_t y2, uint32_t s2) {
          float lo, hi;
          asm("{\n.reg .b16 l, h;\nmov.b32 {l, h}, %2;\ncvt.f32.f16 %0, l;\ncvt.f32.f16 %1, h;\n}\n" : "=f"(lo), "=f"(hi) : "r"(y2));
          return bmul2(q2, bmul2(pack_bf16(lo, hi), s2));
        };
#pragma unroll 1
        for (int j = hw ? hw - 1 : 15; j < (hw ? 16 - F4 : 16); j += 3) {
          uint32_t y[4][4];
          uint2 q[8];
          while (hw && (uint32_t)clock() - t0 < j * PACE) __nanosleep(40);
          const uint32_t qj = qa + j * 2048;
#pragma unroll
          for (int i = 0; i < 4; i++) ldsm4t(y[i], ya + j * 128 + (yx ^ (i << 5)));
#pragma unroll
          for (int i = 0; i < 8; i++) q[i] = lds64(qj + (i >> 2) * 1024 + (i & 3) * 128);
#pragma unroll
          for (int i = 0; i < 8; i++) {
            og[(size_t)(j * 64 + (i >> 2) * 32 + (i & 3) * 2) * (2 * DM / 4)] =
                make_uint2(fin(q[i].x, y[i >> 1][2 * (i & 1)], sc[0]), fin(q[i].y, y[i >> 1][2 * (i & 1) + 1], sc[1]));
            if (i < 7) asm volatile("nanosleep.u32 %0;\n" ::"r"(FINE) : "memory");
          }
        }
      }
      PROF(22);
    }
    cluster_sync_all();
  } else {
    asm volatile("setmaxnreg.inc.sync.aligned.u32 %0;\n" :: "n"(REG_MATH));
    if (warp == 0) PROF2(26);
    const int wg = warp >> 2;
    const int wtid = tid & 127;
    const bool signaller = (wtid == 0) || (wtid == 32);
    const uint32_t rbars = mapa(bars, wtid >> 5 & 1);

    if (halo_cta) {
      const uint32_t epoch = ld_relaxed(g_flag_h + blockIdx.x) + 1;
      float acc0[64], acc1[64];
      int s = 0, ph = 0;
#pragma unroll 1
      for (int kb = 0; kb < 16; kb++) {
        mbar_wait(bars + 8 * (BAR_FULLB + s), ph);
        const uint32_t st = sb + s * STGH;
        const uint64_t da = mkdesc(st, 16, 1024, 1);
        const uint64_t db = mkdesc(st + 8192 + wg * 32768, 8192, 1024, 1);
        wg_fence();
#pragma unroll
        for (int kk = 0; kk < 4; kk++) {
          wgmma_n128(acc0, da + 2 * kk, db + 128 * kk, kb + kk);
          wgmma_n128(acc1, da + 2 * kk, db + 1024 + 128 * kk, kb + kk);
        }
        wg_commit();
        wg_wait<0>();
        if (wtid == 0) mbar_arrive(bars + 8 * (BAR_EMPTYB + s));
        if (++s == 3) { s = 0; ph ^= 1; }
      }
      fence_regs(acc0);
      fence_regs(acc1);
      if ((warp & 3) != 3) {
#pragma unroll
        for (int hh = 0; hh < 2; hh++) {
          uint4* dst = g_halo + ((hh * 4 + (warp & 3) + 1) * 16 + blockIdx.x * 4) * 128 + wg * 64 + lane;
#pragma unroll
          for (int j = 0; j < 4; j++) {
            const int o = 16 * j + 2 * hh;
            dst[(j >> 1) * 128 + (j & 1) * 32] =
                make_uint4(pack_bf16(acc0[o], acc0[o + 1]), pack_bf16(acc0[o + 4], acc0[o + 5]),
                           pack_bf16(acc0[o + 8], acc0[o + 9]), pack_bf16(acc0[o + 12], acc0[o + 13]));
            dst[(2 + (j >> 1)) * 128 + (j & 1) * 32] =
                make_uint4(pack_bf16(acc1[o], acc1[o + 1]), pack_bf16(acc1[o + 4], acc1[o + 5]),
                           pack_bf16(acc1[o + 8], acc1[o + 9]), pack_bf16(acc1[o + 12], acc1[o + 13]));
          }
        }
      }
      nb_sync(NB_G1DONE, 256);
      if (tid == 0) st_release(g_flag_h + blockIdx.x, epoch);
      PROF(36);
      cluster_sync_all();
      return;
    }

    float acc[64];
    auto g2_step = [&](int s, int kb) {
      const uint64_t da = mkdesc(sb + g2_a(s) + wg * 8192, 16, 1024, 1);
      const uint64_t db = mkdesc(sb + g2_b(s), 8192, 1024, 1);
      wg_fence();
      wgmma_n128(acc, da, db, kb);
      wgmma_n128(acc, da + 2, db + 128, 1);
      wgmma_n128(acc, da + 4, db + 256, 1);
      wgmma_n128(acc, da + 6, db + 384, 1);
      wg_commit();
    };

    if (MODE != 2) {
    uint32_t a1[2][4], tw[16], d1[32];
    const uint32_t tb = sb + OFF_T + wtid * 16;
    const uint64_t dx = mkdesc(sb + OFF_U + wg * 4096, OFF_H - OFF_U, 1024, 1);
    auto s1 = [&](int it) {
      hmma_n128t<0>(d1, a1[0], dx + it * 512);
      hmma_n128t<1>(d1, a1[1], dx + it * 512 + 128);
      wg_commit();
    };
    auto ldtw = [&](int i) {
      const uint4 v = lds128(tb + T_TW + i * 2048);
      tw[4 * i] = v.x; tw[4 * i + 1] = v.y; tw[4 * i + 2] = v.z; tw[4 * i + 3] = v.w;
    };
    {
      float acc0[96], acc1[96];
      int sa = 0, pha = 0, sbb = 0, phb = 0;
      asm volatile("cp.async.wait_group 0;\n" ::: "memory");
      fence_async_smem();
      nb_sync(NB_FIRST, 256);
      if (tid == 0) {
        mbar_arrive(bars + 8 * BAR_FULLA);
        mbar_arrive(bars + 8 * BAR_FULLB);
      }
      PROF(0 + wg);
#pragma unroll 1
      for (int kb = 0; kb < 30; kb++) {
        if (!(kb & 1)) mbar_wait(bars + 8 * (BAR_FULLA + sa), pha);
        mbar_wait(bars + 8 * (BAR_FULLB + sbb), phb);
        if (kb == 0) PROF2(0 + wg);
        if (kb == 4 && wg == 0) PROF2(28);
        if (kb == 8 && wg == 0) PROF2(29);
        if (kb == 16 && wg == 0) PROF2(30);
        const uint64_t da = mkdesc(sb + sa * STG1A + wg * 16384 + (kb & 1) * 64, 16, 1024, 1);
        const uint64_t db = mkdesc(sb + OFF_1B + sbb * STG1B, 4096, 1024, 1);
        wg_fence();
        wgmma_n192(acc0, da, db, kb);
        wgmma_n192(acc1, da + 512, db, kb);
        wgmma_n192(acc0, da + 2, db + 128, 1);
        wgmma_n192(acc1, da + 514, db + 128, 1);
        wg_commit();
        wg_wait<1>();
        if (kb > 0) {
          if (wtid == 64) mbar_arrive(bars + 8 * (BAR_EMPTYB + (sbb == 0 ? NS1B - 1 : sbb - 1)));
          if (!(kb & 1) && signaller) mbar_arrive_cluster(rbars + 8 * (BAR_EMPTYA + (sa == 0 ? NS1A - 1 : sa - 1)));
        }
        if (++sbb == NS1B) { sbb = 0; phb ^= 1; }
        if ((kb & 1) && ++sa == NS1A) { sa = 0; pha ^= 1; }
      }
      const int blk0 = wg * 8 + (warp & 3);
      const int lr = lane & 7, lm = lane >> 3;
      const bool le0 = 2 * (lane & 3) <= (lane >> 2), le1 = 2 * (lane & 3) + 1 <= (lane >> 2);
      const uint32_t maskLE = (le0 ? 0x0000FFFFu : 0u) | (le1 ? 0xFFFF0000u : 0u);
      uint32_t k0[2][2][4], k1[2][2][4], qa[2][2][8];
      float l[2][2][4];
      {
        static_assert(15 % NS1A == 0 && 30 % NS1B == 0, "slots of the last k blocks");
        mbar_wait(bars + 8 * BAR_FULLA, 1);
        mbar_wait(bars + 8 * BAR_FULLB, 0);
        mbar_wait(bars + 8 * (BAR_FULLB + 1), 0);
        const uint64_t da = mkdesc(sb + wg * 16384, 16, 1024, 1);
        const uint64_t db = mkdesc(sb + OFF_1B, 4096, 1024, 1);
        wg_fence();
#pragma unroll
        for (int i = 0; i < 4; i++) wgmma_n192(acc0, da + 2 * i, db + (i >> 1) * (STG1B >> 4) + (i & 1) * 128, 1);
        wg_commit();
        wg_wait<1>();
        if (wtid == 64) mbar_arrive(bars + 8 * (BAR_EMPTYB + NS1B - 1));
#pragma unroll
        for (int i = 0; i < 2; i++) wgmma_n192(acc1, da + 512 + 2 * i, db + (i >> 1) * (STG1B >> 4) + (i & 1) * 128, 1);
        wg_commit();
        wg_wait<1>();
        fence_regs(acc0);
        attn_stage(sb, blk0, lane, acc0, k1[0]);
#pragma unroll
        for (int i = 2; i < 4; i++) wgmma_n192(acc1, da + 512 + 2 * i, db + (i >> 1) * (STG1B >> 4) + (i & 1) * 128, 1);
        wg_commit();
        attn_pack(acc0, qa[0], k0[0]);
        wg_wait<0>();
        fence_regs(acc1);
      }
      if (wtid == 64) mbar_arrive(bars + 8 * BAR_EMPTYB);
      PROF(2 + wg);
      attn_stage(sb, blk0 + 4, lane, acc1, k1[1]);
      __syncwarp();
      if (lane == 0) mbar_arrive(bars + 8 * BAR_STG);
      mbar_wait(bars + 8 * BAR_U, 0);
      attn_pack(acc1, qa[1], k0[1]);
      attn_own(k0[0], k1[0], le0, le1, qa[0], l[0]);
      attn_own(k0[1], k1[1], le0, le1, qa[1], l[1]);
      static_assert(OFF_L0 + 2048 == OFF_VP, "halo V rows");
      const uint32_t vl0 = sb + OFF_VP - 1024 + blk0 * 2048 + (lm >> 1) * 1024 + lr * 128 + (((lm & 1) ^ lr) << 4);
      const uint32_t vl[4] = {vl0, vl0 ^ 64, vl0 ^ 32, vl0 ^ 96};
      const uint32_t obase = sb + OFF_OP + (wg == (rb2 & 1) ? 16384 : 0) + ((warp & 3) * 16 + lr) * 128 + ((lm ^ lr) << 4);
      mbar_wait(bars + 8 * BAR_STG, 0);
      {
        uint32_t km[4][4], va[8][4], vb[8][4], pp[8];
        float x[8][2];
#pragma unroll
        for (int n = 0; n < 4; n++) {
          const int blk = blk0 + 4 * (n >> 1);
          to_arr(km[n], lds128(sb + (blk == 0 ? OFF_L0 : OFF_KH + (blk - 1) * 2048) + (n & 1) * 512 + lane * 16));
        }
#pragma unroll
        for (int n = 0; n < 8; n++) {
          const uint32_t o = ((n >> 1) & 1) * 8192 + (n >> 2) * 1024;
          ldsm4t(va[n], vl[n & 1] + o);
          ldsm4t(vb[n], vl[2 + (n & 1)] + o);
        }
        const bool first = blk0 == 0 && gidx == 0;
#pragma unroll
        for (int n = 0; n < 4; n++) {
          const uint32_t(&q)[8] = qa[n >> 1][n & 1];
          float sm[4];
          mma16816_z(sm, q[0], q[1], q[2], q[3], km[n][0], km[n][1]);
          mma16816(sm, q[4], q[5], q[6], q[7], km[n][2], km[n][3]);
          if (n < 2 && first) sm[0] = sm[1] = -1e9f / 0.17677669529663687f;
          x[n][0] = le0 ? l[n >> 1][n & 1][0] : sm[0];
          x[n][1] = le1 ? l[n >> 1][n & 1][1] : sm[1];
          x[4 + n][0] = l[n >> 1][n & 1][2];
          x[4 + n][1] = l[n >> 1][n & 1][3];
        }
        quad_softmax<8>(x, pp);
#pragma unroll
        for (int n = 7; n >= 0; n--)
          attn_pv((obase ^ ((n & 1) << 6)) + ((n >> 1) & 1) * 8192 + (n >> 2) * 1024, va[n], vb[n], pp[n], maskLE);
      }
      fence_async_smem();
      nb_arrive(NB_OREADY + wg, 160);
    }

    {
      const int w = warp & 3;
      uint32_t a4[8][4];
      uint32_t d4[16];
      PROF(34 + wg);
      const uint64_t dz = mkdesc(sb + OFF_U + wg * 4096, 1024, 128, 0);
      const uint64_t db2 = mkdesc(sb + OFF_T + T_B2, 128, 256, 0);
      mbar_wait(bars + 8 * BAR_T, 0);
      mbar_wait(bars + 8 * BAR_UH, 0);
      to_arr(a1[0], lds128(tb + T_A1));
      to_arr(a1[1], lds128(tb + T_A1 + 2048));
      wg_fence();
      s1(0);
      ldtw(0);
      ldtw(1);
      const uint32_t za = sb + (w < 2 ? OFF_U : OFF_H) + wg * 4096 + (w & 1) * 8192 + lane * 16;
      const uint32_t yl = (wtid ^ (4 * rank + wg)) * 16;
      const uint32_t yown = mapa(sb, rank) + yl, yrem = mapa(sb + OFF_LAND + wg * 2048, rank ^ 1) + yl;
      const uint32_t yb[2] = {mapa(bars + 8 * BAR_LAND, 0), mapa(bars + 8 * BAR_LAND, 1)};
      wg_wait<0>();
      fence_regs(d1);
      auto s4 = [&]() {
        wg_fence();
#pragma unroll
        for (int ks = 0; ks < 8; ks++) {
          const uint64_t d = dz + (ks & 1) * 128 + ((ks >> 1) & 1) * 512 + (ks >> 2) * ((OFF_H - OFF_U) >> 4);
          if (ks == 0) hmma_n64t<0>(d4, a4[ks], d);
          else hmma_n64t<1>(d4, a4[ks], d);
        }
        wg_commit();
      };
      auto e4 = [&](int pr) {
        fence_regs(d4);
        mbar_wait(bars + 8 * (pr == 0 ? BAR_LFREE : BAR_DEAD + 1), 0);
#pragma unroll
        for (int u = 0; u < 2; u++) {
          const int it = 2 * pr + u;
          const uint32_t o = (yown + y_slot(wg, it)) ^ (pr << 5), m = (yrem + it * 4096) ^ (pr << 5);
          st_async128(rank ? m : o, yb[0], d4[8 * u], d4[8 * u + 1], d4[8 * u + 2], d4[8 * u + 3]);
          st_async128(rank ? o : m, yb[1], d4[8 * u + 4], d4[8 * u + 5], d4[8 * u + 6], d4[8 * u + 7]);
        }
      };
      uint32_t a2[2][2][2][4], a3[2][2][4], d2[2][2][8], d3[2][8];
      auto s2a = [&]() {
        wg_fence();
#pragma unroll
        for (int c = 0; c < 4; c++) hmma_n32<0, 0>(d2[c & 1][c >> 1], a2[0][c & 1][c >> 1], db2 + (c >> 1) * 128);
      };
      auto s2b = [&]() {
        wg_fence();
#pragma unroll
        for (int c = 0; c < 4; c++) {
          hmma_n32<1, 0>(d2[c & 1][c >> 1], a2[1][c & 1][c >> 1], db2 + (c >> 1) * 128 + 64);
          if (c & 1) wg_commit();
        }
      };
      fft_e1<0>(d1, tw, a2[0]);
      s2a();
      fft_e1<1>(d1, tw, a2[1]);
      s2b();
      s1(1);
      ldtw(2);
      ldtw(3);
#pragma unroll
      for (int i = 0; i < 8; i++) to_arr(a4[i], lds128(tb + T_A4 + i * 2048));
#pragma unroll
      for (int it = 0; it < 4; it++) {
        if (it == 2) wg_wait<3>(); else if (it == 3) wg_wait<1>(); else wg_wait<2>();
        fence_regs(d2[0][0]);
        fence_regs(d2[1][0]);
        fft_e2<0, 0>(d2[0][0], d2[1][0], a3[0]);
        fft_e2<0, 1>(d2[0][0], d2[1][0], a3[1]);
        if (it == 2) wg_wait<2>(); else if (it == 3) wg_wait<0>(); else wg_wait<1>();
        fence_regs(d2[0][1]);
        fence_regs(d2[1][1]);
        fft_e2<1, 0>(d2[0][1], d2[1][1], a3[0]);
        fft_e2<1, 1>(d2[0][1], d2[1][1], a3[1]);
        wg_fence();
        hmma_n32<0, 0>(d3[0], a3[0][0], db2);
        hmma_n32<0, 0>(d3[1], a3[0][1], db2);
        hmma_n32<1, 0>(d3[0], a3[1][0], db2 + 64);
        hmma_n32<1, 0>(d3[1], a3[1][1], db2 + 64);
        wg_commit();
        if (it < 3) {
          wg_wait<1>();
          if (it == 2) {
            if (wtid == 64) mbar_arrive(bars + 8 * BAR_DEAD);
            e4(0);
          }
          fence_regs(d1);
          fft_e1<0>(d1, tw, a2[0]);
          s2a();
          wg_commit();
          wg_wait<1>();
        }
        if (ORD == 0 || it == 3) wg_wait<0>();
        if (it == 3 && wtid == 64) mbar_arrive(bars + 8 * (BAR_DEAD + 1));
        fence_regs(d3[0]);
        fence_regs(d3[1]);
        if (ORD == 0 && it < 3) s2a();
        fft_e3(d3, tw, za + (it & 1) * 512);
        if (ORD != 2 && it < 3) {
          fft_e1<1>(d1, tw, a2[1]);
          s2b();
        }
        if (it & 1) {
          fence_async_smem();
          nb_sync(NB_WG + wg, 128);
          if (it == 1 && signaller) mbar_arrive_cluster(rbars + 8 * BAR_LFREE);
          s4();
        }
        if (it < 2) s1(it + 2);
        if (w == 0) PROF3(40 + 4 * wg + it);
      }
      if (PEEL && MODE == 0) {
        mbar_wait(bars + 8 * BAR_FULL2, 0);
        g2_step(0, 0);
        wg_wait<1>();
      } else {
        wg_wait<0>();
      }
      if (signaller) mbar_arrive_cluster(rbars + 8 * (BAR_EMPTY2 + 4));
      e4(1);
      if (PEEL && MODE == 0) {
        wg_wait<0>();
        if (signaller) mbar_arrive_cluster(rbars + 8 * BAR_EMPTY2);
      }
      PROF(6 + wg);
    }
    }

    if (MODE != 1) {
      int s = PEEL && MODE == 0, ph = 0;
#pragma unroll 1
      for (int kb = s; kb < STAG; kb++) {
        mbar_wait(bars + 8 * (BAR_FULL2 + s), ph);
        if (kb == 1) PROF(8 + wg);
        if (warp == 4) PROF2(40 + kb);
        g2_step(s, kb);
        wg_wait<0>();
        if (kb < 16 - NS2 && signaller) mbar_arrive_cluster(rbars + 8 * (BAR_EMPTY2 + s));
        if (++s == NS2) { s = 0; ph ^= 1; }
      }
      if (STAG < 16) {
        if (wg == LAST) nb_sync(NB_LEAD, 256);
#pragma unroll
        for (int kb = STAG; kb < 16; kb++) {
          mbar_wait(bars + 8 * (BAR_FULL2 + kb % NS2), (kb / NS2) & 1);
          g2_step(kb % NS2, 1);
        }
        if (wg != LAST) nb_arrive(NB_LEAD, 256);
      }
      wg_wait<0>();
      fence_regs(acc);
      PROF(10 + wg);
      const int lr = lane & 7, lm = lane >> 3;
      const uint32_t wbase = sb + warp * 2048;
      const uint32_t base = wbase + (lr + 8 * (lm & 1)) * 128;
#pragma unroll
      for (int j = 0; j < 16; j += 2) {
        const uint32_t a = base + (j >> 3) * 16384 + ((((j & 7) + (lm >> 1)) ^ lr) << 4);
        stsm4(a, pack_bf16(acc[4 * j], acc[4 * j + 1]), pack_bf16(acc[4 * j + 2], acc[4 * j + 3]),
              pack_bf16(acc[4 * j + 4], acc[4 * j + 5]), pack_bf16(acc[4 * j + 6], acc[4 * j + 7]));
      }
      if (TST == 2 || (TST == 1 && wg != LAST)) {
        fence_async_smem();
        __syncwarp();
        if (elect_one()) {
#pragma unroll
          for (int hf = 0; hf < 2; hf++)
            asm volatile("cp.async.bulk.tensor.3d.global.shared::cta.bulk_group [%0, {%2, %3, %4}], [%1];\n"
                         ::"l"(&tmO), "r"(wbase + hf * 16384), "r"(cb2 * 128 + hf * 64), "r"(rb2 >> 3), "r"((rb2 & 7) * 128 + warp * 16) : "memory");
          bulk_commit();
          bulk_wait0();
        }
        __syncwarp();
      } else {
        __syncwarp();
        const int rr = lane >> 4, ck = lane & 7, hf = (lane >> 3) & 1;
        uint4* og = reinterpret_cast<uint4*>(p.out + (size_t)(2 * ((rb2 & 7) * 128 + warp * 16 + rr) + (rb2 >> 3)) * (2 * DM) + DM + cb2 * 128 + hf * 64 + ck * 8);
        uint4 v[8];
#pragma unroll
        for (int i = 0; i < 8; i++) v[i] = lds128(wbase + hf * 16384 + (2 * i + rr) * 128 + ((ck ^ ((2 * i + rr) & 7)) << 4));
#pragma unroll
        for (int i = 0; i < 8; i++) og[(size_t)i * 4 * (2 * DM / 8)] = v[i];
      }
      PROF(12 + wg);
    }
    cluster_sync_all();
  }
}

typedef CUresult (*EncodeFn)(CUtensorMap*, CUtensorMapDataType, cuuint32_t, void*, const cuuint64_t*, const cuuint64_t*,
                             const cuuint32_t*, const cuuint32_t*, CUtensorMapInterleave, CUtensorMapSwizzle,
                             CUtensorMapL2promotion, CUtensorMapFloatOOBfill);

void make_map(EncodeFn enc, CUtensorMap* tm, const void* base, int rank, const cuuint64_t* dims, const cuuint64_t* strides,
              const cuuint32_t* box, CUtensorMapSwizzle swz) {
  cuuint32_t es[5] = {1, 1, 1, 1, 1};
  enc(tm, CU_TENSOR_MAP_DATA_TYPE_BFLOAT16, rank, const_cast<void*>(base), dims, strides, box, es,
      CU_TENSOR_MAP_INTERLEAVE_NONE, swz, CU_TENSOR_MAP_L2_PROMOTION_L2_256B, CU_TENSOR_MAP_FLOAT_OOB_FILL_NONE);
}

}

extern "C" void kernel_launch(void* const* d_in, const int* in_sizes, int n_in, void* d_out, int out_size) {
  static EncodeFn enc = nullptr;
  static bool coresident = true;
  if (!enc) {
    void* fn = nullptr;
    cudaDriverEntryPointQueryResult qr;
    cudaGetDriverEntryPoint("cuTensorMapEncodeTiled", &fn, cudaEnableDefault, &qr);
    enc = (EncodeFn)fn;
    cudaFuncSetAttribute(fused_kernel<0>, cudaFuncAttributeMaxDynamicSharedMemorySize, SMEM_BYTES);
    cudaFuncSetAttribute(fused_kernel<1>, cudaFuncAttributeMaxDynamicSharedMemorySize, SMEM_BYTES);
    cudaFuncSetAttribute(fused_kernel<2>, cudaFuncAttributeMaxDynamicSharedMemorySize, SMEM_BYTES);
    cudaLaunchConfig_t cfg = {};
    cfg.gridDim = dim3(NCTA);
    cfg.blockDim = dim3(NTHREADS);
    cfg.dynamicSmemBytes = SMEM_BYTES;
    cudaLaunchAttribute at;
    at.id = cudaLaunchAttributeClusterDimension;
    at.val.clusterDim.x = 2;
    at.val.clusterDim.y = 1;
    at.val.clusterDim.z = 1;
    cfg.attrs = &at;
    cfg.numAttrs = 1;
    int nclusters = 0;
    if (cudaOccupancyMaxActiveClusters(&nclusters, fused_kernel<0>, &cfg) == cudaSuccess) coresident = nclusters >= NCTA / 2;
    (void)cudaGetLastError();
  }
  CUtensorMap tmX, tmW, tmWo, tmQ, tmO, tmXh, tmWh;
  {
    cuuint64_t dims[3] = {1024, 2, 1024};
    cuuint64_t str[2] = {2048, 4096};
    cuuint32_t box[3] = {64, 1, 128};
    make_map(enc, &tmX, d_in[6], 3, dims, str, box, CU_TENSOR_MAP_SWIZZLE_128B);
  }
  {
    cuuint64_t dims[3] = {1024, 1024, 3};
    cuuint64_t str[2] = {6144, 2048};
    cuuint32_t box[3] = {64, 32, 3};
    make_map(enc, &tmW, d_in[7], 3, dims, str, box, CU_TENSOR_MAP_SWIZZLE_128B);
  }
  {
    cuuint64_t dims[3] = {64, 1024, 16};
    cuuint64_t str[2] = {2048, 128};
    cuuint32_t box[3] = {64, 64, 2};
    make_map(enc, &tmWo, d_in[8], 3, dims, str, box, CU_TENSOR_MAP_SWIZZLE_128B);
  }
  {
    cuuint64_t dims[5] = {1024, 2, 2, 8, 64};
    cuuint64_t str[4] = {2048, 16 * 2048, 2 * 2048, 32 * 2048};
    cuuint32_t box[5] = {16, 2, 2, 8, 4};
    make_map(enc, &tmQ, d_in[0], 5, dims, str, box, CU_TENSOR_MAP_SWIZZLE_NONE);
  }
  {
    cuuint64_t dims[3] = {1024, 2, 1024};
    cuuint64_t str[2] = {4096, 8192};
    cuuint32_t box[3] = {64, 1, 16};
    make_map(enc, &tmO, (const __nv_bfloat16*)d_out + DM, 3, dims, str, box, CU_TENSOR_MAP_SWIZZLE_128B);
  }
  {
    cuuint64_t dims[4] = {1024, 256, 2, 4};
    cuuint64_t str[3] = {4096, 2048, 256 * 4096};
    cuuint32_t box[4] = {64, 8, 2, 4};
    make_map(enc, &tmXh, d_in[6], 4, dims, str, box, CU_TENSOR_MAP_SWIZZLE_128B);
  }
  {
    cuuint64_t dims[3] = {64, 1024, 48};
    cuuint64_t str[2] = {6144, 128};
    cuuint32_t box[3] = {64, 64, 4};
    make_map(enc, &tmWh, d_in[7], 3, dims, str, box, CU_TENSOR_MAP_SWIZZLE_128B);
  }
  Params p;
  p.q = (const __nv_bfloat16*)d_in[0];
  p.k = (const __nv_bfloat16*)d_in[1];
  p.v = (const __nv_bfloat16*)d_in[2];
  p.shift_k = (const __nv_bfloat16*)d_in[3];
  p.ssm_k = (const __nv_bfloat16*)d_in[4];
  p.ssm_D = (const __nv_bfloat16*)d_in[5];
  p.x = (const __nv_bfloat16*)d_in[6];
  p.w = (const __nv_bfloat16*)d_in[7];
  p.wo = (const __nv_bfloat16*)d_in[8];
  p.out = (__nv_bfloat16*)d_out;
  if (coresident) {
    fused_kernel<0><<<NCTA, NTHREADS, SMEM_BYTES>>>(p, tmX, tmW, tmWo, tmQ, tmO, tmXh, tmWh);
  } else {
    fused_kernel<0><<<4, NTHREADS, SMEM_BYTES>>>(p, tmX, tmW, tmWo, tmQ, tmO, tmXh, tmWh);
    fused_kernel<1><<<NCTA, NTHREADS, SMEM_BYTES>>>(p, tmX, tmW, tmWo, tmQ, tmO, tmXh, tmWh);
    fused_kernel<2><<<NCTA, NTHREADS, SMEM_BYTES>>>(p, tmX, tmW, tmWo, tmQ, tmO, tmXh, tmWh);
  }
}
```

```cpp
#include <cuda_runtime.h>
#include <cuda.h>
#include <cuda_bf16.h>
#include <stdint.h>

namespace {

constexpr int SEQ = 2048;
constexpr int DM = 1024;
constexpr int NCTA = 132;
constexpr int NTHREADS = 384;

constexpr int STG1A = 32768;
constexpr int NS1A = 3;
constexpr int STG1B = 12288;
constexpr int NS1B = 5;
constexpr int OFF_1B = NS1A * STG1A;
constexpr int STG2 = 32768;
constexpr int NS2 = 5;
constexpr int STGH = 73728;
constexpr int OFF_VP = 0;
constexpr int OFF_KH = 1 * STG2;
constexpr int OFF_OP = 2 * STG2;
constexpr int OFF_Q = 3 * STG2;
constexpr int T_A4 = 0, T_TW = 16384, T_B2 = 24576, T_A1 = 28672, T_END = 32768;
constexpr int OFF_U = 163840;
constexpr int OFF_H = OFF_U + 32768;
constexpr int OFF_T = OFF_U - T_END;
constexpr int OFF_LAND = 4 * STG2;
constexpr int OFF_BAR = OFF_H + 32768;
constexpr int OFF_SC = OFF_BAR + 512;
constexpr int HALO = 2048;
constexpr int SMEM_BYTES = HALO + OFF_BAR + 1024;
static_assert(OFF_T + T_A1 == OFF_1B + NS1B * STG1B && OFF_T + T_TW == OFF_1B + 4 * STG1B && OFF_LAND == OFF_T + T_A4, "layout");
static_assert(3 * STGH <= OFF_BAR && SMEM_BYTES <= 232448, "smem");

constexpr int BAR_FULLA = 0;
constexpr int BAR_EMPTYA = 3;
constexpr int BAR_FULLB = 6;
constexpr int BAR_EMPTYB = 11;
constexpr int BAR_FULL2 = 16;
constexpr int BAR_EMPTY2 = 21;
constexpr int BAR_T = 26;
constexpr int BAR_UH = 27;
constexpr int BAR_LFREE = 28;
constexpr int BAR_LAND = 29;
constexpr int BAR_U = 30;
constexpr int BAR_Q = 31;
constexpr int BAR_STG = 32;
constexpr int BAR_DEAD = 33;
constexpr int BAR_X = 35;
constexpr int BAR_REL = 36;

constexpr int NB_G1DONE = 1;
constexpr int NB_OREADY = 2;
constexpr int NB_WG = 4;
constexpr int NB_HELP3 = 6;
constexpr int NB_FIRST = 7;
constexpr int NB_LEAD = 8;

constexpr int REG_MATH = 224, REG_HELP = 56;
constexpr int PF0 = 20;
constexpr uint32_t PACE = 390;
constexpr int STAG = 12;
constexpr int SPIN_LIMIT = 1 << 20;

__device__ __align__(1024) __nv_bfloat16 g_o[SEQ * DM];
__device__ __align__(128) uint32_t g_flag_o[256];
__device__ uint32_t g_flag_h[4];
__device__ uint4 g_halo[128 * 128];
__device__ __align__(128) const uint32_t g_tab[T_END / 4] = {
0x3c003c00,0x3bf13bff,0,0xafd6a648,0x3c003c00,0x3b993bce,0,0xb505b303,0x3c003c00,0x3af63b50,0,0xb7e3b67c,
0x3c003c00,0x3a0f3a8a,0,0xb93ab89b,0x3bc33bfe,0x3b773bfa,0xb3c6aa48,0xb5c2acb5,0x3a6d3b3b,0x389b3a4f,0xb8c4b6d7,0xba8ab8ec,
0x381d395f,0x26483505,0xbaddb9ed,0xbbffbb99,0x30b23564,0xb848b444,0xbbeabb88,0xbac2bbb6,0x3b0e3bf6,0x3a8a3bf1,0xb78bae46,0xb89bafd6,
0x34a53913,0xa6483732,0xbba8ba2f,0xbbffbb25,0xb78bae46,0xbac2b7e3,0xbb0ebbf6,0xb848baf6,0xbba8ba2f,0xbb50bbfa,0xb4a5b913,0x367cacb5,
0x39ed3bea,0x393a3be2,0xb95fb0b2,0xba0fb179,0xb56433c6,0xb8ec2648,0xbb88bbc3,0xba4fbbff,0xbbfeba6d,0xbb25bbce,0xaa48b8c4,0x3732b303,
0xb6d7badd,0x3444b67c,0x3b3b381d,0x3bb63b50,0x38723bd9,0x37323bce,0xbaa7b23e,0xbb25b303,0xbaa7b23e,0xbbb6b67c,0xb872bbd9,0xb444bb50,
0xb872bbd9,0xacb5ba8a,0x3aa7323e,0x3bfa389b,0x3aa7323e,0x3bf139cb,0x38723bd9,0xafd63984,0x35643bc3,0x33033bb6,0xbb88b3c6,0xbbceb444,
0xbbfeb8c4,0xbb77ba0f,0x2a48ba6d,0x35c2b93a,0x36d7b81d,0x3a8aafd6,0x3b3b3add,0x389b3bf1,0x395f3bea,0x26483b25,0xb9ed30b2,0xbbffb732,
0x2e463ba8,0xa6483b99,0xbbf6b4a5,0xbbffb505,0xba2fbb0e,0xb848bbb6,0x3913b78b,0x3ac2b444,0x3bf634a5,0x3b50393a,0x2e463ba8,0xb67c3a0f,
0xb913378b,0xbbe2afd6,0xba2fbb0e,0xb179bbf1,0xb0b23b88,0xb4443b77,0xbbeab564,0xbbb6b5c2,0xb3c6bbfe,0x2cb5bbe2,0x3bc3aa48,0x3bfa3179,
0x38c43b3b,0x2fd63bff,0xba6d36d7,0xbbf12648,0xbaddb95f,0xb505bbce,0x381db9ed,0x3b99b303,0xb61f3b64,0xb7e33b50,0xbb64b61f,0xbaf6b67c,
0x361fbb64,0x393aba8a,0x3b64361f,0x3a0f389b,0xb61f3b64,0xba4f3984,0xbb64b61f,0xb8ecb9cb,0x361fbb64,0x3b25b848,0x3b64361f,0x37323ac2,
0xb8c43b3b,0xb9843b25,0xba6db6d7,0xb9cbb732,0x3addb95f,0x3bceb7e3,0x381d39ed,0x33033af6,0xbbea3564,0xbb77acb5,0xb0b2bb88,0x35c2bbfa,
0x3bc32a48,0x389b38ec,0xb3c63bfe,0xba8a3a4f,0xba2f3b0e,0xbac23af6,0xb913b78b,0xb848b7e3,0x3bf6b4a5,0x3b50acb5,0xae463ba8,0xb67c3bfa,
0xb913b78b,0xb179ba4f,0x3a2fbb0e,0x3be2b8ec,0xae463ba8,0xb9cb3b99,0xbbf634a5,0xb984b505,0xbb3b3add,0xbb993ac2,0xb6d7b81d,0xb505b848,
0x39ed30b2,0x37e335c2,0xb95f3bea,0xbaf63b77,0x3564bbc3,0x3a0fbbe2,0x3b88b3c6,0x393a3179,0xbbfe38c4,0xba4f2648,0xaa48ba6d,0x38ecbbff,
0xbbd93aa7,0xbbfa3a8a,0xb23eb872,0xacb5b89b,0x323e3872,0xafd639cb,0xbbd93aa7,0xbbf13984,0x3bd9baa7,0x3b99b848,0x323e3872,0xb5053ac2,
0xb23eb872,0x37e3bb77,0x3bd9baa7,0x3af6b5c2,0xbbfe3a6d,0xbbe23a4f,0x2a48b8c4,0x3179b8ec,0xb6d73add,0xb9843b99,0xbb3b381d,0xb9cb3505,
0x395fb0b2,0x33033444,0xb9ed3bea,0xbbce3bb6,0x3b88bbc3,0x3b77b93a,0x356433c6,0xb5c23a0f,0xbba83a2f,0xbb503a0f,0x34a5b913,0x367cb93a,
0xbb0e3bf6,0xbbe23bf1,0xb78b2e46,0xb179afd6,0xb4a53913,0xb9cb3b25,0xbba83a2f,0xb9843732,0x378bae46,0xb30337e3,0xbb0e3bf6,0xbbce3af6,
0xbadd39ed,0xba4f39cb,0x381db95f,0x38ecb984,0xbbea3b88,0xbb253ac2,0x30b2b564,0x3732b848,0xbbc33bfe,0xbbb63b77,0xb3c62a48,0x3444b5c2,
0xba6d3b3b,0xbbfa3be2,0xb8c436d7,0x2cb5b179,0xb9a839a8,0xb8ec3984,0x39a8b9a8,0x3a4fb9cb,0xb9a839a8,0xb7323848,0x39a8b9a8,0x3b25bac2,
0xb9a839a8,0xb44435c2,0x39a8b9a8,0x3bb6bb77,0xb9a839a8,0xacb53179,0x39a8b9a8,0x3bfabbe2,0xb81d395f,0xb67c393a,0x3addb9ed,0x3b50ba0f,
0xb0b23564,0x31792fd6,0x3beabb88,0x3be2bbf1,0x33c6aa48,0x3984b732,0x3bc3bbfe,0x39cbbb25,0x38c4b6d7,0x3bcebaf6,0x3a6dbb3b,0x3303b7e3,
0xb4a53913,0xb17938ec,0x3ba8ba2f,0x3be2ba4f,0x378bae46,0x39cbb505,0x3b0ebbf6,0x3984bb99,0x3ba8ba2f,0x3bcebbb6,0x34a5b913,0xb303b444,
0x3b0ebbf6,0x35c2ba0f,0xb78b2e46,0xbb77393a,0xaa4838c4,0x2cb5389b,0x3bfeba6d,0x3bfaba8a,0x3b3bb81d,0x3bf1b984,0x36d7badd,0x2fd6b9cb,
0x39edbbea,0x3505bac2,0xb95f30b2,0xbb993848,0xb564b3c6,0xbaf635c2,0xbb883bc3,0xb7e33b77,0x323e3872,0x35053848,0x3bd9baa7,0x3b99bac2,
0x3bd9baa7,0x3af6bb77,0xb23eb872,0xb7e3b5c2,0xb23eb872,0xb93ab179,0xbbd93aa7,0xba0f3be2,0xbbd93aa7,0xb8ec3bff,0x323e3872,0x3a4fa648,
0x36d7381d,0x384837e3,0x3b3bbadd,0x3ac2baf6,0x395fbbea,0x367cbbfa,0xb9edb0b2,0xbb502cb5,0xbb8833c6,0xbbe238ec,0xb5643bc3,0x31793a4f,
0x2a483a6d,0x39843505,0x3bfeb8c4,0x39cbbb99,0x3913378b,0x39cb3732,0x3a2fbb0e,0x3984bb25,0x2e46bba8,0xb303baf6,0xbbf634a5,0xbbce37e3,
0xba2f3b0e,0xb5c23bfa,0x3913378b,0x3b772cb5,0x3bf6b4a5,0x3a8aba4f,0x2e46bba8,0xb89bb8ec,0x3a6d36d7,0x3af6367c,0x38c4bb3b,0x37e3bb50,
0xb81db9ed,0xba0fb89b,0xbadd395f,0xb93a3a8a,0x30b23b88,0x38ec39cb,0x3beab564,0x3a4fb984,0x33c6bbfe,0xb732bac2,0xbbc3aa48,0xbb253848,
0x3b64361f,0x3bb635c2,0x361fbb64,0x3444bb77,0xbb64b61f,0xbbfab179,0xb61f3b64,0xacb53be2,0x3b64361f,0x3bf1a648,0x361fbb64,0xafd6bbff,
0xbb64b61f,0xbb993303,0xb61f3b64,0x35053bce,0x3bea3564,0x3bff3505,0x30b2bb88,0x2648bb99,0xbbc32a48,0xbac23444,0x33c63bfe,0x38483bb6,
0x3a6db6d7,0x367cba0f,0xb8c4bb3b,0xbb50b93a,0xb81d39ed,0x31793bf1,0x3add395f,0x3be22fd6,0x3bf634a5,0x3bce3444,0xae46bba8,0xb303bbb6,
0xb913378b,0xb5c2393a,0x3a2f3b0e,0x3b773a0f,0xae46bba8,0xb89bbbf1,0xbbf6b4a5,0xba8a2fd6,0x3a2f3b0e,0x3bff3732,0x3913b78b,0xa648bb25,
0x3b8833c6,0x3b253303,0xb564bbc3,0xb732bbce,0xaa483a6d,0x34443b50,0x3bfe38c4,0x3bb6367c,0xbb3bbadd,0xbbfab89b,0xb6d7381d,0x2cb53a8a,
0x39edb0b2,0x2fd6b984,0xb95fbbea,0xbbf1b9cb,0x3aa7323e,0x3a0f3179,0xb872bbd9,0xb93abbe2,0x38723bd9,0x3a4f3bff,0x3aa7323e,0x38eca648,
0xbaa7b23e,0xb7323303,0x38723bd9,0x3b253bce,0xb872bbd9,0xbbb6bb50,0xbaa7b23e,0xb444367c,0x395f30b2,0x389b2fd6,0xb9edbbea,0xba8abbf1,
0x3b883bc3,0x3bff3b25,0x3564b3c6,0x2648b732,0x2a4838c4,0x38483af6,0x3bfe3a6d,0x3ac237e3,0xbb3bb81d,0xb67c2cb5,0x36d73add,0x3b503bfa,
0x378b2e46,0x35c22cb5,0xbb0ebbf6,0xbb77bbfa,0x3ba83a2f,0x3a8a38ec,0xb4a5b913,0xb89bba4f,0x3b0e3bf6,0x3bff3b99,0x378b2e46,0xa648b505,
0x34a53913,0x3ac23bb6,0x3ba83a2f,0x38483444,0x33c62a48,0x2fd62648,0xbbc3bbfe,0xbbf1bbff,0x38c436d7,0x35053303,0xba6dbb3b,0xbb99bbce,
0x3add39ed,0x37e3367c,0xb81db95f,0xbaf6bb50,0x3bea3b88,0x393a389b,0xb0b2b564,0xba0fba8a,0x3c003c00,0xbbf1bbff,0,0x2fd62648,
0x3c003c00,0xbb99bbce,0,0x35053303,0x3c003c00,0xbaf6bb50,0,0x37e3367c,0x3c003c00,0xba0fba8a,0,0x393a389b,
0x3bc33bfe,0xbb77bbfa,0xb3c6aa48,0x35c22cb5,0x3a6d3b3b,0xb89bba4f,0xb8c4b6d7,0x3a8a38ec,0x381d395f,0xa648b505,0xbaddb9ed,0x3bff3b99,
0x30b23564,0x38483444,0xbbeabb88,0x3ac23bb6,0x3b0e3bf6,0xba8abbf1,0xb78bae46,0x389b2fd6,0x34a53913,0x2648b732,0xbba8ba2f,0x3bff3b25,
0xb78bae46,0x3ac237e3,0xbb0ebbf6,0x38483af6,0xbba8ba2f,0x3b503bfa,0xb4a5b913,0xb67c2cb5,0x39ed3bea,0xb93abbe2,0xb95fb0b2,0x3a0f3179,
0xb56433c6,0x38eca648,0xbb88bbc3,0x3a4f3bff,0xbbfeba6d,0x3b253bce,0xaa48b8c4,0xb7323303,0xb6d7badd,0xb444367c,0x3b3b381d,0xbbb6bb50,
0x38723bd9,0xb732bbce,0xbaa7b23e,0x3b253303,0xbaa7b23e,0x3bb6367c,0xb872bbd9,0x34443b50,0xb872bbd9,0x2cb53a8a,0x3aa7323e,0xbbfab89b,
0x3aa7323e,0xbbf1b9cb,0x38723bd9,0x2fd6b984,0x35643bc3,0xb303bbb6,0xbb88b3c6,0x3bce3444,0xbbfeb8c4,0x3b773a0f,0x2a48ba6d,0xb5c2393a,
0x36d7b81d,0xba8a2fd6,0x3b3b3add,0xb89bbbf1,0x395f3bea,0xa648bb25,0xb9ed30b2,0x3bff3732,0x2e463ba8,0x2648bb99,0xbbf6b4a5,0x3bff3505,
0xba2fbb0e,0x38483bb6,0x3913b78b,0xbac23444,0x3bf634a5,0xbb50b93a,0x2e463ba8,0x367cba0f,0xb913378b,0x3be22fd6,0xba2fbb0e,0x31793bf1,
0xb0b23b88,0x3444bb77,0xbbeab564,0x3bb635c2,0xb3c6bbfe,0xacb53be2,0x3bc3aa48,0xbbfab179,0x38c43b3b,0xafd6bbff,0xba6d36d7,0x3bf1a648,
0xbaddb95f,0x35053bce,0x381db9ed,0xbb993303,0xb61f3b64,0x37e3bb50,0xbb64b61f,0x3af6367c,0x361fbb64,0xb93a3a8a,0x3b64361f,0xba0fb89b,
0xb61f3b64,0x3a4fb984,0xbb64b61f,0x38ec39cb,0x361fbb64,0xbb253848,0x3b64361f,0xb732bac2,0xb8c43b3b,0x3984bb25,0xba6db6d7,0x39cb3732,
0x3addb95f,0xbbce37e3,0x381d39ed,0xb303baf6,0xbbea3564,0x3b772cb5,0xb0b2bb88,0xb5c23bfa,0x3bc32a48,0xb89bb8ec,0xb3c63bfe,0x3a8aba4f,
0xba2f3b0e,0x3ac2baf6,0xb913b78b,0x384837e3,0x3bf6b4a5,0xbb502cb5,0xae463ba8,0x367cbbfa,0xb913b78b,0x31793a4f,0x3a2fbb0e,0xbbe238ec,
0xae463ba8,0x39cbbb99,0xbbf634a5,0x39843505,0xbb3b3add,0x3b99bac2,0xb6d7b81d,0x35053848,0x39ed30b2,0xb7e3b5c2,0xb95f3bea,0x3af6bb77,
0x3564bbc3,0xba0f3be2,0x3b88b3c6,0xb93ab179,0xbbfe38c4,0x3a4fa648,0xaa48ba6d,0xb8ec3bff,0xbbd93aa7,0x3bfaba8a,0xb23eb872,0x2cb5389b,
0x323e3872,0x2fd6b9cb,0xbbd93aa7,0x3bf1b984,0x3bd9baa7,0xbb993848,0x323e3872,0x3505bac2,0xb23eb872,0xb7e33b77,0x3bd9baa7,0xbaf635c2,
0xbbfe3a6d,0x3be2ba4f,0x2a48b8c4,0xb17938ec,0xb6d73add,0x3984bb99,0xbb3b381d,0x39cbb505,0x395fb0b2,0xb303b444,0xb9ed3bea,0x3bcebbb6,
0x3b88bbc3,0xbb77393a,0x356433c6,0x35c2ba0f,0xbba83a2f,0x3b50ba0f,0x34a5b913,0xb67c393a,0xbb0e3bf6,0x3be2bbf1,0xb78b2e46,0x31792fd6,
0xb4a53913,0x39cbbb25,0xbba83a2f,0x3984b732,0x378bae46,0x3303b7e3,0xbb0e3bf6,0x3bcebaf6,0xbadd39ed,0x3a4fb9cb,0x381db95f,0xb8ec3984,
0xbbea3b88,0x3b25bac2,0x30b2b564,0xb7323848,0xbbc33bfe,0x3bb6bb77,0xb3c62a48,0xb44435c2,0xba6d3b3b,0x3bfabbe2,0xb8c436d7,0xacb53179,
0xb9a839a8,0x38ecb984,0x39a8b9a8,0xba4f39cb,0xb9a839a8,0x3732b848,0x39a8b9a8,0xbb253ac2,0xb9a839a8,0x3444b5c2,0x39a8b9a8,0xbbb63b77,
0xb9a839a8,0x2cb5b179,0x39a8b9a8,0xbbfa3be2,0xb81d395f,0x367cb93a,0x3addb9ed,0xbb503a0f,0xb0b23564,0xb179afd6,0x3beabb88,0xbbe23bf1,
0x33c6aa48,0xb9843732,0x3bc3bbfe,0xb9cb3b25,0x38c4b6d7,0xbbce3af6,0x3a6dbb3b,0xb30337e3,0xb4a53913,0x3179b8ec,0x3ba8ba2f,0xbbe23a4f,
0x378bae46,0xb9cb3505,0x3b0ebbf6,0xb9843b99,0x3ba8ba2f,0xbbce3bb6,0x34a5b913,0x33033444,0x3b0ebbf6,0xb5c23a0f,0xb78b2e46,0x3b77b93a,
0xaa4838c4,0xacb5b89b,0x3bfeba6d,0xbbfa3a8a,0x3b3bb81d,0xbbf13984,0x36d7badd,0xafd639cb,0x39edbbea,0xb5053ac2,0xb95f30b2,0x3b99b848,
0xb564b3c6,0x3af6b5c2,0xbb883bc3,0x37e3bb77,0x323e3872,0xb505b848,0x3bd9baa7,0xbb993ac2,0x3bd9baa7,0xbaf63b77,0xb23eb872,0x37e335c2,
0xb23eb872,0x393a3179,0xbbd93aa7,0x3a0fbbe2,0xbbd93aa7,0x38ecbbff,0x323e3872,0xba4f2648,0x36d7381d,0xb848b7e3,0x3b3bbadd,0xbac23af6,
0x395fbbea,0xb67c3bfa,0xb9edb0b2,0x3b50acb5,0xbb8833c6,0x3be2b8ec,0xb5643bc3,0xb179ba4f,0x2a483a6d,0xb984b505,0x3bfeb8c4,0xb9cb3b99,
0x3913378b,0xb9cbb732,0x3a2fbb0e,0xb9843b25,0x2e46bba8,0x33033af6,0xbbf634a5,0x3bceb7e3,0xba2f3b0e,0x35c2bbfa,0x3913378b,0xbb77acb5,
0x3bf6b4a5,0xba8a3a4f,0x2e46bba8,0x389b38ec,0x3a6d36d7,0xbaf6b67c,0x38c4bb3b,0xb7e33b50,0xb81db9ed,0x3a0f389b,0xbadd395f,0x393aba8a,
0x30b23b88,0xb8ecb9cb,0x3beab564,0xba4f3984,0x33c6bbfe,0x37323ac2,0xbbc3aa48,0x3b25b848,0x3b64361f,0xbbb6b5c2,0x361fbb64,0xb4443b77,
0xbb64b61f,0x3bfa3179,0xb61f3b64,0x2cb5bbe2,0x3b64361f,0xbbf12648,0x361fbb64,0x2fd63bff,0xbb64b61f,0x3b99b303,0xb61f3b64,0xb505bbce,
0x3bea3564,0xbbffb505,0x30b2bb88,0xa6483b99,0xbbc32a48,0x3ac2b444,0x33c63bfe,0xb848bbb6,0x3a6db6d7,0xb67c3a0f,0xb8c4bb3b,0x3b50393a,
0xb81d39ed,0xb179bbf1,0x3add395f,0xbbe2afd6,0x3bf634a5,0xbbceb444,0xae46bba8,0x33033bb6,0xb913378b,0x35c2b93a,0x3a2f3b0e,0xbb77ba0f,
0xae46bba8,0x389b3bf1,0xbbf6b4a5,0x3a8aafd6,0x3a2f3b0e,0xbbffb732,0x3913b78b,0x26483b25,0x3b8833c6,0xbb25b303,0xb564bbc3,0x37323bce,
0xaa483a6d,0xb444bb50,0x3bfe38c4,0xbbb6b67c,0xbb3bbadd,0x3bfa389b,0xb6d7381d,0xacb5ba8a,0x39edb0b2,0xafd63984,0xb95fbbea,0x3bf139cb,
0x3aa7323e,0xba0fb179,0xb872bbd9,0x393a3be2,0x38723bd9,0xba4fbbff,0x3aa7323e,0xb8ec2648,0xbaa7b23e,0x3732b303,0x38723bd9,0xbb25bbce,
0xb872bbd9,0x3bb63b50,0xbaa7b23e,0x3444b67c,0x395f30b2,0xb89bafd6,0xb9edbbea,0x3a8a3bf1,0x3b883bc3,0xbbffbb25,0x3564b3c6,0xa6483732,
0x2a4838c4,0xb848baf6,0x3bfe3a6d,0xbac2b7e3,0xbb3bb81d,0x367cacb5,0x36d73add,0xbb50bbfa,0x378b2e46,0xb5c2acb5,0xbb0ebbf6,0x3b773bfa,
0x3ba83a2f,0xba8ab8ec,0xb4a5b913,0x389b3a4f,0x3b0e3bf6,0xbbffbb99,0x378b2e46,0x26483505,0x34a53913,0xbac2bbb6,0x3ba83a2f,0xb848b444,
0x33c62a48,0xafd6a648,0xbbc3bbfe,0x3bf13bff,0x38c436d7,0xb505b303,0xba6dbb3b,0x3b993bce,0x3add39ed,0xb7e3b67c,0xb81db95f,0x3af63b50,
0x3bea3b88,0xb93ab89b,0xb0b2b564,0x3a0f3a8a,0x3c003c00,0x38ec3984,0,0xba4fb9cb,0x3c003c00,0x37323848,0,0xbb25bac2,
0x3c003c00,0x344435c2,0,0xbbb6bb77,0x3c003c00,0x2cb53179,0,0xbbfabbe2,0xb3c6aa48,0xbb50ba0f,0xbbc3bbfe,0xb67cb93a,
0xb8c4b6d7,0xbbe2bbf1,0xba6dbb3b,0x3179afd6,0xbaddb9ed,0xb9cbbb25,0xb81db95f,0x39843732,0xbbeabb88,0xb303b7e3,0xb0b2b564,0x3bce3af6,
0xbb0ebbf6,0xb179b8ec,0x378b2e46,0x3be23a4f,0xb4a5b913,0x39cb3505,0x3ba83a2f,0x39843b99,0x378b2e46,0x3bce3bb6,0x3b0e3bf6,0xb3033444,
0x3ba83a2f,0x35c23a0f,0x34a53913,0xbb77b93a,0x395f30b2,0x3bfa3a8a,0x39ed3bea,0xacb5389b,0x3b883bc3,0x2fd639cb,0xb56433c6,0xbbf1b984,
0x2a4838c4,0xbb99b848,0xbbfeba6d,0xb505bac2,0xbb3bb81d,0xb7e3bb77,0xb6d7badd,0x3af635c2,0x38723bd9,0xb5053848,0xbaa7b23e,0xbb99bac2,
0xbaa7b23e,0xbaf6bb77,0xb872bbd9,0x37e3b5c2,0xb872bbd9,0x393ab179,0x3aa7323e,0x3a0f3be2,0x3aa7323e,0x38ec3bff,0x38723bd9,0xba4fa648,
0xbb88b3c6,0xbac2baf6,0xb564bbc3,0x3848b7e3,0x2a48ba6d,0x3b502cb5,0x3bfe38c4,0x367c3bfa,0x3b3b3add,0xb1793a4f,0xb6d7381d,0xbbe2b8ec,
0xb9ed30b2,0xb9cbbb99,0xb95fbbea,0x3984b505,0xae46bba8,0x39cbb732,0x3bf634a5,0x39843b25,0x3a2f3b0e,0xb3033af6,0xb913378b,0xbbceb7e3,
0xbbf6b4a5,0xb5c2bbfa,0xae46bba8,0x3b77acb5,0x3913b78b,0x3a8a3a4f,0x3a2f3b0e,0xb89b38ec,0x3bea3564,0x37e33b50,0xb0b23b88,0xbaf6367c,
0xbbc32a48,0xb93aba8a,0xb3c6bbfe,0x3a0fb89b,0x3a6db6d7,0x3a4f3984,0x38c43b3b,0xb8ec39cb,0xb81d39ed,0xbb25b848,0xbaddb95f,0x3732bac2,
0xb61f3b64,0xbbb635c2,0xbb64b61f,0xb444bb77,0x361fbb64,0x3bfab179,0x3b64361f,0x2cb53be2,0xb61f3b64,0xbbf1a648,0xbb64b61f,0x2fd6bbff,
0x361fbb64,0x3b993303,0x3b64361f,0xb5053bce,0xba6db6d7,0xa648bb99,0x38c4bb3b,0x3bffb505,0x381d39ed,0xb8483bb6,0xbadd395f,0xbac2b444,
0xb0b2bb88,0x3b50b93a,0x3beab564,0x367c3a0f,0xb3c63bfe,0xbbe22fd6,0xbbc3aa48,0x3179bbf1,0x3a2fbb0e,0x3bceb444,0x3913378b,0xb3033bb6,
0xbbf634a5,0xb5c2b93a,0x2e46bba8,0x3b77ba0f,0x3913378b,0xb89b3bf1,0xba2f3b0e,0xba8aafd6,0x2e46bba8,0x3bffb732,0x3bf6b4a5,0xa6483b25,
0x36d7381d,0xb7323bce,0xbb3b3add,0xbb253303,0x395fbbea,0x3bb6b67c,0x39ed30b2,0xb4443b50,0xbb8833c6,0x2cb5ba8a,0x3564bbc3,0x3bfab89b,
0x2a483a6d,0xbbf139cb,0xbbfe38c4,0xafd6b984,0xbbd93aa7,0xba0f3179,0xb23eb872,0x393abbe2,0x323e3872,0xba4f3bff,0xbbd93aa7,0xb8eca648,
0x3bd9baa7,0x37323303,0x323e3872,0xbb253bce,0xb23eb872,0x3bb6bb50,0x3bd9baa7,0x3444367c,0x2a48b8c4,0x3a8abbf1,0x3bfeba6d,0x389bafd6,
0xbb3b381d,0xa648b732,0x36d7badd,0x3bffbb25,0xb9ed3bea,0xbac237e3,0xb95f30b2,0x3848baf6,0x356433c6,0xbb503bfa,0xbb883bc3,0xb67cacb5,
0x3ba8ba2f,0x35c2acb5,0xb4a53913,0xbb773bfa,0x3b0ebbf6,0x3a8ab8ec,0x378bae46,0xb89b3a4f,0x34a5b913,0x3bffbb99,0x3ba8ba2f,0xa6483505,
0xb78b2e46,0x3ac2bbb6,0x3b0ebbf6,0x3848b444,0xb81d395f,0xbbf13bff,0xbadd39ed,0xafd62648,0xb0b23564,0xbb993bce,0xbbea3b88,0xb5053303,
0x33c6aa48,0xbaf63b50,0xbbc33bfe,0xb7e3367c,0x38c4b6d7,0xba0f3a8a,0xba6d3b3b,0xb93a389b,0xb9a839a8,0x2fd6a648,0x39a8b9a8,0x3bf1bbff,
0xb9a839a8,0x3505b303,0x39a8b9a8,0x3b99bbce,0xb9a839a8,0x37e3b67c,0x39a8b9a8,0x3af6bb50,0xb9a839a8,0x393ab89b,0x39a8b9a8,0x3a0fba8a,
0x3addb9ed,0x3b77bbfa,0x381db95f,0xb5c22cb5,0x3beabb88,0x389bba4f,0x30b2b564,0xba8a38ec,0x3bc3bbfe,0x2648b505,0xb3c62a48,0xbbff3b99,
0x3a6dbb3b,0xb8483444,0xb8c436d7,0xbac23bb6,0x34a5b913,0xb89b2fd6,0xbba83a2f,0xba8a3bf1,0xb78b2e46,0xbbff3b25,0xbb0e3bf6,0x26483732,
0xbba83a2f,0xb8483af6,0xb4a53913,0x3ac2b7e3,0xbb0e3bf6,0x367c2cb5,0x378bae46,0x3b50bbfa,0xbbfe3a6d,0xb93a3be2,0xaa4838c4,0x3a0fb179,
0xb6d73add,0x38ec2648,0x3b3bb81d,0x3a4fbbff,0x395fb0b2,0x3b25bbce,0x39edbbea,0xb732b303,0x3b88bbc3,0xb444b67c,0xb564b3c6,0xbbb63b50,
0x323e3872,0x3b25b303,0x3bd9baa7,0x3732bbce,0x3bd9baa7,0x3444bb50,0xb23eb872,0xbbb6367c,0xb23eb872,0xbbfa389b,0xbbd93aa7,0xacb53a8a,
0xbbd93aa7,0x2fd63984,0x323e3872,0x3bf1b9cb,0x3b3bbadd,0x3303bbb6,0xb6d7b81d,0xbbce3444,0xb9edb0b2,0xbb773a0f,0xb95f3bea,0x35c2393a,
0xb5643bc3,0x3a8a2fd6,0x3b88b3c6,0x389bbbf1,0x3bfeb8c4,0x2648bb25,0xaa48ba6d,0xbbff3732,0xb913b78b,0xbbff3505,0xba2f3b0e,0x26483b99,
0xae463ba8,0x3ac23444,0x3bf6b4a5,0x3848bbb6,0x3a2fbb0e,0xb67cba0f,0xb913b78b,0xbb50393a,0xbbf634a5,0xb1793bf1,0xae463ba8,0x3be2afd6,
0xb8c43b3b,0x34443b77,0x3a6d36d7,0x3bb6b5c2,0x3addb95f,0xacb5bbe2,0xb81db9ed,0xbbfa3179,0xbbea3564,0xafd63bff,0x30b23b88,0x3bf12648,
0x3bc32a48,0x3505bbce,0x33c6bbfe,0xbb99b303,0x3b64361f,0x3af6b67c,0x361fbb64,0xb7e3bb50,0xbb64b61f,0xba0f389b,0xb61f3b64,0x393a3a8a,
0x3b64361f,0x38ecb9cb,0x361fbb64,0xba4fb984,0xbb64b61f,0xb7323ac2,0xb61f3b64,0x3b253848,0x30b2bb88,0xb984bb25,0xbbeab564,0xb9cb3732,
0x33c63bfe,0x3bce37e3,0x3bc3aa48,0x3303baf6,0xb8c4bb3b,0xbb772cb5,0xba6d36d7,0x35c23bfa,0x3add395f,0x389bb8ec,0x381db9ed,0xba8aba4f,
0xbbf6b4a5,0xb84837e3,0x2e463ba8,0x3ac23af6,0x3913b78b,0xb67cbbfa,0xba2fbb0e,0xbb50acb5,0x2e463ba8,0x3be238ec,0x3bf634a5,0x3179ba4f,
0xba2fbb0e,0xb9843505,0xb913378b,0x39cb3b99,0x35643bc3,0x3b993ac2,0x3b8833c6,0x3505b848,0xbbfeb8c4,0xb7e335c2,0xaa483a6d,0x3af63b77,
0x36d7b81d,0xba0fbbe2,0xbb3bbadd,0xb93a3179,0x395f3bea,0x3a4f2648,0x39edb0b2,0xb8ecbbff,0x3aa7323e,0x2cb5b89b,0xb872bbd9,0xbbfaba8a,
0x38723bd9,0x3bf13984,0x3aa7323e,0xafd6b9cb,0xbaa7b23e,0x35053ac2,0x38723bd9,0x3b993848,0xb872bbd9,0xbaf6b5c2,0xbaa7b23e,0x37e33b77,
0xb9edbbea,0xbbe2ba4f,0xb95fb0b2,0x317938ec,0x3564b3c6,0xb984bb99,0xbb88bbc3,0xb9cbb505,0x3bfe3a6d,0x3303b444,0xaa48b8c4,0xbbcebbb6,
0x36d73add,0x3b77393a,0x3b3b381d,0xb5c2ba0f,0xb78bae46,0x367c393a,0x3b0e3bf6,0x3b503a0f,0xbba8ba2f,0xb1792fd6,0x34a53913,0x3be23bf1,
0xbb0ebbf6,0xb984b732,0xb78bae46,0x39cb3b25,0xb4a5b913,0xbbcebaf6,0xbba8ba2f,0x330337e3,0x3bc33bfe,0x3a4f39cb,0x33c62a48,0xb8ecb984,
0x3a6d3b3b,0x3b253ac2,0x38c436d7,0xb732b848,0x381d395f,0x3bb63b77,0x3add39ed,0xb444b5c2,0x30b23564,0x3bfa3be2,0x3bea3b88,0xacb5b179,
0x3c003c00,0xb8ecb984,0,0x3a4f39cb,0x3c003c00,0xb732b848,0,0x3b253ac2,0x3c003c00,0xb444b5c2,0,0x3bb63b77,
0x3c003c00,0xacb5b179,0,0x3bfa3be2,0xb3c6aa48,0x3b503a0f,0xbbc3bbfe,0x367c393a,0xb8c4b6d7,0x3be23bf1,0xba6dbb3b,0xb1792fd6,
0xbaddb9ed,0x39cb3b25,0xb81db95f,0xb984b732,0xbbeabb88,0x330337e3,0xb0b2b564,0xbbcebaf6,0xbb0ebbf6,0x317938ec,0x378b2e46,0xbbe2ba4f,
0xb4a5b913,0xb9cbb505,0x3ba83a2f,0xb984bb99,0x378b2e46,0xbbcebbb6,0x3b0e3bf6,0x3303b444,0x3ba83a2f,0xb5c2ba0f,0x34a53913,0x3b77393a,
0x395f30b2,0xbbfaba8a,0x39ed3bea,0x2cb5b89b,0x3b883bc3,0xafd6b9cb,0xb56433c6,0x3bf13984,0x2a4838c4,0x3b993848,0xbbfeba6d,0x35053ac2,
0xbb3bb81d,0x37e33b77,0xb6d7badd,0xbaf6b5c2,0x38723bd9,0x3505b848,0xbaa7b23e,0x3b993ac2,0xbaa7b23e,0x3af63b77,0xb872bbd9,0xb7e335c2,
0xb872bbd9,0xb93a3179,0x3aa7323e,0xba0fbbe2,0x3aa7323e,0xb8ecbbff,0x38723bd9,0x3a4f2648,0xbb88b3c6,0x3ac23af6,0xb564bbc3,0xb84837e3,
0x2a48ba6d,0xbb50acb5,0x3bfe38c4,0xb67cbbfa,0x3b3b3add,0x3179ba4f,0xb6d7381d,0x3be238ec,0xb9ed30b2,0x39cb3b99,0xb95fbbea,0xb9843505,
0xae46bba8,0xb9cb3732,0x3bf634a5,0xb984bb25,0x3a2f3b0e,0x3303baf6,0xb913378b,0x3bce37e3,0xbbf6b4a5,0x35c23bfa,0xae46bba8,0xbb772cb5,
0x3913b78b,0xba8aba4f,0x3a2f3b0e,0x389bb8ec,0x3bea3564,0xb7e3bb50,0xb0b23b88,0x3af6b67c,0xbbc32a48,0x393a3a8a,0xb3c6bbfe,0xba0f389b,
0x3a6db6d7,0xba4fb984,0x38c43b3b,0x38ecb9cb,0xb81d39ed,0x3b253848,0xbaddb95f,0xb7323ac2,0xb61f3b64,0x3bb6b5c2,0xbb64b61f,0x34443b77,
0x361fbb64,0xbbfa3179,0x3b64361f,0xacb5bbe2,0xb61f3b64,0x3bf12648,0xbb64b61f,0xafd63bff,0x361fbb64,0xbb99b303,0x3b64361f,0x3505bbce,
0xba6db6d7,0x26483b99,0x38c4bb3b,0xbbff3505,0x381d39ed,0x3848bbb6,0xbadd395f,0x3ac23444,0xb0b2bb88,0xbb50393a,0x3beab564,0xb67cba0f,
0xb3c63bfe,0x3be2afd6,0xbbc3aa48,0xb1793bf1,0x3a2fbb0e,0xbbce3444,0x3913378b,0x3303bbb6,0xbbf634a5,0x35c2393a,0x2e46bba8,0xbb773a0f,
0x3913378b,0x389bbbf1,0xba2f3b0e,0x3a8a2fd6,0x2e46bba8,0xbbff3732,0x3bf6b4a5,0x2648bb25,0x36d7381d,0x3732bbce,0xbb3b3add,0x3b25b303,
0x395fbbea,0xbbb6367c,0x39ed30b2,0x3444bb50,0xbb8833c6,0xacb53a8a,0x3564bbc3,0xbbfa389b,0x2a483a6d,0x3bf1b9cb,0xbbfe38c4,0x2fd63984,
0xbbd93aa7,0x3a0fb179,0xb23eb872,0xb93a3be2,0x323e3872,0x3a4fbbff,0xbbd93aa7,0x38ec2648,0x3bd9baa7,0xb732b303,0x323e3872,0x3b25bbce,
0xb23eb872,0xbbb63b50,0x3bd9baa7,0xb444b67c,0x2a48b8c4,0xba8a3bf1,0x3bfeba6d,0xb89b2fd6,0xbb3b381d,0x26483732,0x36d7badd,0xbbff3b25,
0xb9ed3bea,0x3ac2b7e3,0xb95f30b2,0xb8483af6,0x356433c6,0x3b50bbfa,0xbb883bc3,0x367c2cb5,0x3ba8ba2f,0xb5c22cb5,0xb4a53913,0x3b77bbfa,
0x3b0ebbf6,0xba8a38ec,0x378bae46,0x389bba4f,0x34a5b913,0xbbff3b99,0x3ba8ba2f,0x2648b505,0xb78b2e46,0xbac23bb6,0x3b0ebbf6,0xb8483444,
0xb81d395f,0x3bf1bbff,0xbadd39ed,0x2fd6a648,0xb0b23564,0x3b99bbce,0xbbea3b88,0x3505b303,0x33c6aa48,0x3af6bb50,0xbbc33bfe,0x37e3b67c,
0x38c4b6d7,0x3a0fba8a,0xba6d3b3b,0x393ab89b,0xb9a839a8,0xafd62648,0x39a8b9a8,0xbbf13bff,0xb9a839a8,0xb5053303,0x39a8b9a8,0xbb993bce,
0xb9a839a8,0xb7e3367c,0x39a8b9a8,0xbaf63b50,0xb9a839a8,0xb93a389b,0x39a8b9a8,0xba0f3a8a,0x3addb9ed,0xbb773bfa,0x381db95f,0x35c2acb5,
0x3beabb88,0xb89b3a4f,0x30b2b564,0x3a8ab8ec,0x3bc3bbfe,0xa6483505,0xb3c62a48,0x3bffbb99,0x3a6dbb3b,0x3848b444,0xb8c436d7,0x3ac2bbb6,
0x34a5b913,0x389bafd6,0xbba83a2f,0x3a8abbf1,0xb78b2e46,0x3bffbb25,0xbb0e3bf6,0xa648b732,0xbba83a2f,0x3848baf6,0xb4a53913,0xbac237e3,
0xbb0e3bf6,0xb67cacb5,0x378bae46,0xbb503bfa,0xbbfe3a6d,0x393abbe2,0xaa4838c4,0xba0f3179,0xb6d73add,0xb8eca648,0x3b3bb81d,0xba4f3bff,
0x395fb0b2,0xbb253bce,0x39edbbea,0x37323303,0x3b88bbc3,0x3444367c,0xb564b3c6,0x3bb6bb50,0x323e3872,0xbb253303,0x3bd9baa7,0xb7323bce,
0x3bd9baa7,0xb4443b50,0xb23eb872,0x3bb6b67c,0xb23eb872,0x3bfab89b,0xbbd93aa7,0x2cb5ba8a,0xbbd93aa7,0xafd6b984,0x323e3872,0xbbf139cb,
0x3b3bbadd,0xb3033bb6,0xb6d7b81d,0x3bceb444,0xb9edb0b2,0x3b77ba0f,0xb95f3bea,0xb5c2b93a,0xb5643bc3,0xba8aafd6,0x3b88b3c6,0xb89b3bf1,
0x3bfeb8c4,0xa6483b25,0xaa48ba6d,0x3bffb732,0xb913b78b,0x3bffb505,0xba2f3b0e,0xa648bb99,0xae463ba8,0xbac2b444,0x3bf6b4a5,0xb8483bb6,
0x3a2fbb0e,0x367c3a0f,0xb913b78b,0x3b50b93a,0xbbf634a5,0x3179bbf1,0xae463ba8,0xbbe22fd6,0xb8c43b3b,0xb444bb77,0x3a6d36d7,0xbbb635c2,
0x3addb95f,0x2cb53be2,0xb81db9ed,0x3bfab179,0xbbea3564,0x2fd6bbff,0x30b23b88,0xbbf1a648,0x3bc32a48,0xb5053bce,0x33c6bbfe,0x3b993303,
0x3b64361f,0xbaf6367c,0x361fbb64,0x37e33b50,0xbb64b61f,0x3a0fb89b,0xb61f3b64,0xb93aba8a,0x3b64361f,0xb8ec39cb,0x361fbb64,0x3a4f3984,
0xbb64b61f,0x3732bac2,0xb61f3b64,0xbb25b848,0x30b2bb88,0x39843b25,0xbbeab564,0x39cbb732,0x33c63bfe,0xbbceb7e3,0x3bc3aa48,0xb3033af6,
0xb8c4bb3b,0x3b77acb5,0xba6d36d7,0xb5c2bbfa,0x3add395f,0xb89b38ec,0x381db9ed,0x3a8a3a4f,0xbbf6b4a5,0x3848b7e3,0x2e463ba8,0xbac2baf6,
0x3913b78b,0x367c3bfa,0xba2fbb0e,0x3b502cb5,0x2e463ba8,0xbbe2b8ec,0x3bf634a5,0xb1793a4f,0xba2fbb0e,0x3984b505,0xb913378b,0xb9cbbb99,
0x35643bc3,0xbb99bac2,0x3b8833c6,0xb5053848,0xbbfeb8c4,0x37e3b5c2,0xaa483a6d,0xbaf6bb77,0x36d7b81d,0x3a0f3be2,0xbb3bbadd,0x393ab179,
0x395f3bea,0xba4fa648,0x39edb0b2,0x38ec3bff,0x3aa7323e,0xacb5389b,0xb872bbd9,0x3bfa3a8a,0x38723bd9,0xbbf1b984,0x3aa7323e,0x2fd639cb,
0xbaa7b23e,0xb505bac2,0x38723bd9,0xbb99b848,0xb872bbd9,0x3af635c2,0xbaa7b23e,0xb7e3bb77,0xb9edbbea,0x3be23a4f,0xb95fb0b2,0xb179b8ec,
0x3564b3c6,0x39843b99,0xbb88bbc3,0x39cb3505,0x3bfe3a6d,0xb3033444,0xaa48b8c4,0x3bce3bb6,0x36d73add,0xbb77b93a,0x3b3b381d,0x35c23a0f,
0xb78bae46,0xb67cb93a,0x3b0e3bf6,0xbb50ba0f,0xbba8ba2f,0x3179afd6,0x34a53913,0xbbe2bbf1,0xbb0ebbf6,0x39843732,0xb78bae46,0xb9cbbb25,
0xb4a5b913,0x3bce3af6,0xbba8ba2f,0xb303b7e3,0x3bc33bfe,0xba4fb9cb,0x33c62a48,0x38ec3984,0x3a6d3b3b,0xbb25bac2,0x38c436d7,0x37323848,
0x381d395f,0xbbb6bb77,0x3add39ed,0x344435c2,0x30b23564,0xbbfabbe2,0x3bea3b88,0x2cb53179,0x3c003c00,0xafd6a648,0,0xbbf1bbff,
0x3c003c00,0xb505b303,0,0xbb99bbce,0x3c003c00,0xb7e3b67c,0,0xbaf6bb50,0x3c003c00,0xb93ab89b,0,0xba0fba8a,
0xbbc3bbfe,0x35c22cb5,0x33c62a48,0x3b773bfa,0xba6dbb3b,0x3a8a38ec,0x38c436d7,0x389b3a4f,0xb81db95f,0x3bff3b99,0x3add39ed,0x26483505,
0xb0b2b564,0x3ac23bb6,0x3bea3b88,0xb848b444,0x3b0e3bf6,0xb89bafd6,0xb78bae46,0xba8abbf1,0x34a53913,0xbbffbb25,0xbba8ba2f,0x2648b732,
0xb78bae46,0xb848baf6,0xbb0ebbf6,0x3ac237e3,0xbba8ba2f,0x367cacb5,0xb4a5b913,0x3b503bfa,0xb9edbbea,0x3a0f3179,0x395f30b2,0x393a3be2,
0x3564b3c6,0x3a4f3bff,0x3b883bc3,0xb8ec2648,0x3bfe3a6d,0xb7323303,0x2a4838c4,0xbb25bbce,0x36d73add,0xbbb6bb50,0xbb3bb81d,0x3444b67c,
0x38723bd9,0xbb25b303,0xbaa7b23e,0xb732bbce,0xbaa7b23e,0xb444bb50,0xb872bbd9,0x3bb6367c,0xb872bbd9,0x3bfa389b,0x3aa7323e,0x2cb53a8a,
0x3aa7323e,0xafd63984,0x38723bd9,0xbbf1b9cb,0xb564bbc3,0x3bce3444,0x3b8833c6,0x33033bb6,0x3bfe38c4,0xb5c2393a,0xaa483a6d,0xbb77ba0f,
0xb6d7381d,0xb89bbbf1,0xbb3bbadd,0x3a8aafd6,0xb95fbbea,0x3bff3732,0x39edb0b2,0x26483b25,0x2e463ba8,0xbbffb505,0xbbf6b4a5,0x2648bb99,
0xba2fbb0e,0x3ac2b444,0x3913b78b,0x38483bb6,0x3bf634a5,0xb67c3a0f,0x2e463ba8,0xbb50b93a,0xb913378b,0xb179bbf1,0xba2fbb0e,0x3be22fd6,
0x30b2bb88,0x3bb635c2,0x3bea3564,0xb4443b77,0x33c63bfe,0xbbfab179,0xbbc32a48,0x2cb5bbe2,0xb8c4bb3b,0x3bf1a648,0x3a6db6d7,0x2fd63bff,
0x3add395f,0xbb993303,0xb81d39ed,0xb505bbce,0xb61f3b64,0xbaf6b67c,0xbb64b61f,0x37e3bb50,0x361fbb64,0x3a0f389b,0x3b64361f,0xb93a3a8a,
0xb61f3b64,0xb8ecb9cb,0xbb64b61f,0x3a4fb984,0x361fbb64,0x37323ac2,0x3b64361f,0xbb253848,0x38c4bb3b,0x39cb3732,0x3a6d36d7,0xb9843b25,
0xbadd395f,0xb303baf6,0xb81db9ed,0x3bceb7e3,0x3beab564,0xb5c23bfa,0x30b23b88,0xbb77acb5,0xbbc3aa48,0x3a8aba4f,0x33c6bbfe,0x389b38ec,
0xba2f3b0e,0xb848b7e3,0xb913b78b,0x3ac2baf6,0x3bf6b4a5,0xb67c3bfa,0xae463ba8,0xbb502cb5,0xb913b78b,0x3be2b8ec,0x3a2fbb0e,0x31793a4f,
0xae463ba8,0xb984b505,0xbbf634a5,0x39cbbb99,0x3b3bbadd,0x35053848,0x36d7381d,0xbb993ac2,0xb9edb0b2,0x3af6bb77,0x395fbbea,0x37e335c2,
0xb5643bc3,0xb93ab179,0xbb8833c6,0x3a0fbbe2,0x3bfeb8c4,0xb8ec3bff,0x2a483a6d,0xba4f2648,0xbbd93aa7,0xacb5b89b,0xb23eb872,0x3bfaba8a,
0x323e3872,0xbbf13984,0xbbd93aa7,0x2fd6b9cb,0x3bd9baa7,0xb5053ac2,0x323e3872,0xbb993848,0xb23eb872,0x3af6b5c2,0x3bd9baa7,0xb7e33b77,
0x3bfeba6d,0xb17938ec,0xaa4838c4,0xbbe23a4f,0x36d7badd,0x39cbb505,0x3b3bb81d,0xb9843b99,0xb95f30b2,0x3bcebbb6,0x39edbbea,0x33033444,
0xbb883bc3,0x35c2ba0f,0xb564b3c6,0x3b77b93a,0xbba83a2f,0x367cb93a,0x34a5b913,0x3b50ba0f,0xbb0e3bf6,0xb179afd6,0xb78b2e46,0x3be2bbf1,
0xb4a53913,0xb9843732,0xbba83a2f,0x39cbbb25,0x378bae46,0xbbce3af6,0xbb0e3bf6,0x3303b7e3,0x3addb9ed,0xb8ec3984,0xb81d395f,0xba4f39cb,
0x3beabb88,0xb7323848,0xb0b23564,0xbb253ac2,0x3bc3bbfe,0xb44435c2,0x33c6aa48,0xbbb63b77,0x3a6dbb3b,0xacb53179,0x38c4b6d7,0xbbfa3be2,
0xb9a839a8,0x3a4fb9cb,0x39a8b9a8,0x38ecb984,0xb9a839a8,0x3b25bac2,0x39a8b9a8,0x3732b848,0xb9a839a8,0x3bb6bb77,0x39a8b9a8,0x3444b5c2,
0xb9a839a8,0x3bfabbe2,0x39a8b9a8,0x2cb5b179,0x381db95f,0xbb503a0f,0xbadd39ed,0xb67c393a,0x30b2b564,0xbbe23bf1,0xbbea3b88,0x31792fd6,
0xb3c62a48,0xb9cb3b25,0xbbc33bfe,0x3984b732,0xb8c436d7,0xb30337e3,0xba6d3b3b,0x3bcebaf6,0xb4a53913,0x3be2ba4f,0x3ba8ba2f,0x3179b8ec,
0x378bae46,0x3984bb99,0x3b0ebbf6,0xb9cb3505,0x3ba8ba2f,0xb303b444,0x34a5b913,0xbbce3bb6,0x3b0ebbf6,0xbb77393a,0xb78b2e46,0xb5c23a0f,
0x2a48b8c4,0xbbfa3a8a,0xbbfe3a6d,0x2cb5389b,0xbb3b381d,0xafd639cb,0xb6d73add,0x3bf1b984,0xb9ed3bea,0x3b99b848,0x395fb0b2,0x3505bac2,
0x356433c6,0x37e3bb77,0x3b88bbc3,0xbaf635c2,0x323e3872,0x3b99bac2,0x3bd9baa7,0xb505b848,0x3bd9baa7,0xb7e3b5c2,0xb23eb872,0xbaf63b77,
0xb23eb872,0xba0f3be2,0xbbd93aa7,0x393a3179,0xbbd93aa7,0x3a4fa648,0x323e3872,0x38ecbbff,0xb6d7b81d,0xbac23af6,0xbb3b3add,0x384837e3,
0xb95f3bea,0x3b50acb5,0x39ed30b2,0x367cbbfa,0x3b88b3c6,0xb179ba4f,0x3564bbc3,0xbbe238ec,0xaa48ba6d,0xb9cb3b99,0xbbfe38c4,0x39843505,
0x3913378b,0x3984bb25,0x3a2fbb0e,0xb9cbb732,0x2e46bba8,0xbbce37e3,0xbbf634a5,0x33033af6,0xba2f3b0e,0x3b772cb5,0x3913378b,0x35c2bbfa,
0x3bf6b4a5,0xb89bb8ec,0x2e46bba8,0xba8a3a4f,0xba6db6d7,0xb7e33b50,0xb8c43b3b,0x3af6367c,0x381d39ed,0x393aba8a,0x3addb95f,0xba0fb89b,
0xb0b2bb88,0xba4f3984,0xbbea3564,0x38ec39cb,0xb3c63bfe,0x3b25b848,0x3bc32a48,0xb732bac2,0x3b64361f,0x3444bb77,0x361fbb64,0xbbb6b5c2,
0xbb64b61f,0xacb53be2,0xb61f3b64,0x3bfa3179,0x3b64361f,0xafd6bbff,0x361fbb64,0xbbf12648,0xbb64b61f,0x35053bce,0xb61f3b64,0x3b99b303,
0xbbeab564,0xa6483b99,0xb0b23b88,0x3bff3505,0x3bc3aa48,0xb848bbb6,0xb3c6bbfe,0xbac23444,0xba6d36d7,0x3b50393a,0x38c43b3b,0x367cba0f,
0x381db9ed,0xbbe2afd6,0xbaddb95f,0x31793bf1,0x3bf634a5,0xb303bbb6,0xae46bba8,0xbbceb444,0xb913378b,0x3b773a0f,0x3a2f3b0e,0x35c2b93a,
0xae46bba8,0xba8a2fd6,0xbbf6b4a5,0x389b3bf1,0x3a2f3b0e,0xa648bb25,0x3913b78b,0xbbffb732,0xbb88b3c6,0x37323bce,0x35643bc3,0x3b253303,
0x2a48ba6d,0xbbb6b67c,0xbbfeb8c4,0x34443b50,0x3b3b3add,0xacb5ba8a,0x36d7b81d,0xbbfab89b,0xb9ed30b2,0x3bf139cb,0x395f3bea,0x2fd6b984,
0x3aa7323e,0xb93abbe2,0xb872bbd9,0xba0fb179,0x38723bd9,0x38eca648,0x3aa7323e,0xba4fbbff,0xbaa7b23e,0x3b253bce,0x38723bd9,0x3732b303,
0xb872bbd9,0xb444367c,0xbaa7b23e,0x3bb63b50,0xb95fb0b2,0x3a8a3bf1,0x39ed3bea,0x389b2fd6,0xbb88bbc3,0xa6483732,0xb56433c6,0x3bff3b25,
0xaa48b8c4,0xbac2b7e3,0xbbfeba6d,0x38483af6,0x3b3b381d,0xbb50bbfa,0xb6d7badd,0xb67c2cb5,0x378b2e46,0xbb77bbfa,0xbb0ebbf6,0xb5c2acb5,
0x3ba83a2f,0xb89bba4f,0xb4a5b913,0xba8ab8ec,0x3b0e3bf6,0xa648b505,0x378b2e46,0xbbffbb99,0x34a53913,0x38483444,0x3ba83a2f,0xbac2bbb6,
0xb3c6aa48,0x3bf13bff,0x3bc33bfe,0x2fd62648,0xb8c4b6d7,0x3b993bce,0x3a6d3b3b,0x35053303,0xbaddb9ed,0x3af63b50,0x381d395f,0x37e3367c,
0xbbeabb88,0x3a0f3a8a,0x30b23564,0x393a389b,0x3c003c00,0x2fd62648,0,0x3bf13bff,0x3c003c00,0x35053303,0,0x3b993bce,
0x3c003c00,0x37e3367c,0,0x3af63b50,0x3c003c00,0x393a389b,0,0x3a0f3a8a,0xbbc3bbfe,0xb5c2acb5,0x33c62a48,0xbb77bbfa,
0xba6dbb3b,0xba8ab8ec,0x38c436d7,0xb89bba4f,0xb81db95f,0xbbffbb99,0x3add39ed,0xa648b505,0xb0b2b564,0xbac2bbb6,0x3bea3b88,0x38483444,
0x3b0e3bf6,0x389b2fd6,0xb78bae46,0x3a8a3bf1,0x34a53913,0x3bff3b25,0xbba8ba2f,0xa6483732,0xb78bae46,0x38483af6,0xbb0ebbf6,0xbac2b7e3,
0xbba8ba2f,0xb67c2cb5,0xb4a5b913,0xbb50bbfa,0xb9edbbea,0xba0fb179,0x395f30b2,0xb93abbe2,0x3564b3c6,0xba4fbbff,0x3b883bc3,0x38eca648,
0x3bfe3a6d,0x3732b303,0x2a4838c4,0x3b253bce,0x36d73add,0x3bb63b50,0xbb3bb81d,0xb444367c,0x38723bd9,0x3b253303,0xbaa7b23e,0x37323bce,
0xbaa7b23e,0x34443b50,0xb872bbd9,0xbbb6b67c,0xb872bbd9,0xbbfab89b,0x3aa7323e,0xacb5ba8a,0x3aa7323e,0x2fd6b984,0x38723bd9,0x3bf139cb,
0xb564bbc3,0xbbceb444,0x3b8833c6,0xb303bbb6,0x3bfe38c4,0x35c2b93a,0xaa483a6d,0x3b773a0f,0xb6d7381d,0x389b3bf1,0xbb3bbadd,0xba8a2fd6,
0xb95fbbea,0xbbffb732,0x39edb0b2,0xa648bb25,0x2e463ba8,0x3bff3505,0xbbf6b4a5,0xa6483b99,0xba2fbb0e,0xbac23444,0x3913b78b,0xb848bbb6,
0x3bf634a5,0x367cba0f,0x2e463ba8,0x3b50393a,0xb913378b,0x31793bf1,0xba2fbb0e,0xbbe2afd6,0x30b2bb88,0xbbb6b5c2,0x3bea3564,0x3444bb77,
0x33c63bfe,0x3bfa3179,0xbbc32a48,0xacb53be2,0xb8c4bb3b,0xbbf12648,0x3a6db6d7,0xafd6bbff,0x3add395f,0x3b99b303,0xb81d39ed,0x35053bce,
0xb61f3b64,0x3af6367c,0xbb64b61f,0xb7e33b50,0x361fbb64,0xba0fb89b,0x3b64361f,0x393aba8a,0xb61f3b64,0x38ec39cb,0xbb64b61f,0xba4f3984,
0x361fbb64,0xb732bac2,0x3b64361f,0x3b25b848,0x38c4bb3b,0xb9cbb732,0x3a6d36d7,0x3984bb25,0xbadd395f,0x33033af6,0xb81db9ed,0xbbce37e3,
0x3beab564,0x35c2bbfa,0x30b23b88,0x3b772cb5,0xbbc3aa48,0xba8a3a4f,0x33c6bbfe,0xb89bb8ec,0xba2f3b0e,0x384837e3,0xb913b78b,0xbac23af6,
0x3bf6b4a5,0x367cbbfa,0xae463ba8,0x3b50acb5,0xb913b78b,0xbbe238ec,0x3a2fbb0e,0xb179ba4f,0xae463ba8,0x39843505,0xbbf634a5,0xb9cb3b99,
0x3b3bbadd,0xb505b848,0x36d7381d,0x3b99bac2,0xb9edb0b2,0xbaf63b77,0x395fbbea,0xb7e3b5c2,0xb5643bc3,0x393a3179,0xbb8833c6,0xba0f3be2,
0x3bfeb8c4,0x38ecbbff,0x2a483a6d,0x3a4fa648,0xbbd93aa7,0x2cb5389b,0xb23eb872,0xbbfa3a8a,0x323e3872,0x3bf1b984,0xbbd93aa7,0xafd639cb,
0x3bd9baa7,0x3505bac2,0x323e3872,0x3b99b848,0xb23eb872,0xbaf635c2,0x3bd9baa7,0x37e3bb77,0x3bfeba6d,0x3179b8ec,0xaa4838c4,0x3be2ba4f,
0x36d7badd,0xb9cb3505,0x3b3bb81d,0x3984bb99,0xb95f30b2,0xbbce3bb6,0x39edbbea,0xb303b444,0xbb883bc3,0xb5c23a0f,0xb564b3c6,0xbb77393a,
0xbba83a2f,0xb67c393a,0x34a5b913,0xbb503a0f,0xbb0e3bf6,0x31792fd6,0xb78b2e46,0xbbe23bf1,0xb4a53913,0x3984b732,0xbba83a2f,0xb9cb3b25,
0x378bae46,0x3bcebaf6,0xbb0e3bf6,0xb30337e3,0x3addb9ed,0x38ecb984,0xb81d395f,0x3a4fb9cb,0x3beabb88,0x3732b848,0xb0b23564,0x3b25bac2,
0x3bc3bbfe,0x3444b5c2,0x33c6aa48,0x3bb6bb77,0x3a6dbb3b,0x2cb5b179,0x38c4b6d7,0x3bfabbe2,0xb9a839a8,0xba4f39cb,0x39a8b9a8,0xb8ec3984,
0xb9a839a8,0xbb253ac2,0x39a8b9a8,0xb7323848,0xb9a839a8,0xbbb63b77,0x39a8b9a8,0xb44435c2,0xb9a839a8,0xbbfa3be2,0x39a8b9a8,0xacb53179,
0x381db95f,0x3b50ba0f,0xbadd39ed,0x367cb93a,0x30b2b564,0x3be2bbf1,0xbbea3b88,0xb179afd6,0xb3c62a48,0x39cbbb25,0xbbc33bfe,0xb9843732,
0xb8c436d7,0x3303b7e3,0xba6d3b3b,0xbbce3af6,0xb4a53913,0xbbe23a4f,0x3ba8ba2f,0xb17938ec,0x378bae46,0xb9843b99,0x3b0ebbf6,0x39cbb505,
0x3ba8ba2f,0x33033444,0x34a5b913,0x3bcebbb6,0x3b0ebbf6,0x3b77b93a,0xb78b2e46,0x35c2ba0f,0x2a48b8c4,0x3bfaba8a,0xbbfe3a6d,0xacb5b89b,
0xbb3b381d,0x2fd6b9cb,0xb6d73add,0xbbf13984,0xb9ed3bea,0xbb993848,0x395fb0b2,0xb5053ac2,0x356433c6,0xb7e33b77,0x3b88bbc3,0x3af6b5c2,
0x323e3872,0xbb993ac2,0x3bd9baa7,0x35053848,0x3bd9baa7,0x37e335c2,0xb23eb872,0x3af6bb77,0xb23eb872,0x3a0fbbe2,0xbbd93aa7,0xb93ab179,
0xbbd93aa7,0xba4f2648,0x323e3872,0xb8ec3bff,0xb6d7b81d,0x3ac2baf6,0xbb3b3add,0xb848b7e3,0xb95f3bea,0xbb502cb5,0x39ed30b2,0xb67c3bfa,
0x3b88b3c6,0x31793a4f,0x3564bbc3,0x3be2b8ec,0xaa48ba6d,0x39cbbb99,0xbbfe38c4,0xb984b505,0x3913378b,0xb9843b25,0x3a2fbb0e,0x39cb3732,
0x2e46bba8,0x3bceb7e3,0xbbf634a5,0xb303baf6,0xba2f3b0e,0xbb77acb5,0x3913378b,0xb5c23bfa,0x3bf6b4a5,0x389b38ec,0x2e46bba8,0x3a8aba4f,
0xba6db6d7,0x37e3bb50,0xb8c43b3b,0xbaf6b67c,0x381d39ed,0xb93a3a8a,0x3addb95f,0x3a0f389b,0xb0b2bb88,0x3a4fb984,0xbbea3564,0xb8ecb9cb,
0xb3c63bfe,0xbb253848,0x3bc32a48,0x37323ac2,0x3b64361f,0xb4443b77,0x361fbb64,0x3bb635c2,0xbb64b61f,0x2cb5bbe2,0xb61f3b64,0xbbfab179,
0x3b64361f,0x2fd63bff,0x361fbb64,0x3bf1a648,0xbb64b61f,0xb505bbce,0xb61f3b64,0xbb993303,0xbbeab564,0x2648bb99,0xb0b23b88,0xbbffb505,
0x3bc3aa48,0x38483bb6,0xb3c6bbfe,0x3ac2b444,0xba6d36d7,0xbb50b93a,0x38c43b3b,0xb67c3a0f,0x381db9ed,0x3be22fd6,0xbaddb95f,0xb179bbf1,
0x3bf634a5,0x33033bb6,0xae46bba8,0x3bce3444,0xb913378b,0xbb77ba0f,0x3a2f3b0e,0xb5c2393a,0xae46bba8,0x3a8aafd6,0xbbf6b4a5,0xb89bbbf1,
0x3a2f3b0e,0x26483b25,0x3913b78b,0x3bff3732,0xbb88b3c6,0xb732bbce,0x35643bc3,0xbb25b303,0x2a48ba6d,0x3bb6367c,0xbbfeb8c4,0xb444bb50,
0x3b3b3add,0x2cb53a8a,0x36d7b81d,0x3bfa389b,0xb9ed30b2,0xbbf1b9cb,0x395f3bea,0xafd63984,0x3aa7323e,0x393a3be2,0xb872bbd9,0x3a0f3179,
0x38723bd9,0xb8ec2648,0x3aa7323e,0x3a4f3bff,0xbaa7b23e,0xbb25bbce,0x38723bd9,0xb7323303,0xb872bbd9,0x3444b67c,0xbaa7b23e,0xbbb6bb50,
0xb95fb0b2,0xba8abbf1,0x39ed3bea,0xb89bafd6,0xbb88bbc3,0x2648b732,0xb56433c6,0xbbffbb25,0xaa48b8c4,0x3ac237e3,0xbbfeba6d,0xb848baf6,
0x3b3b381d,0x3b503bfa,0xb6d7badd,0x367cacb5,0x378b2e46,0x3b773bfa,0xbb0ebbf6,0x35c22cb5,0x3ba83a2f,0x389b3a4f,0xb4a5b913,0x3a8a38ec,
0x3b0e3bf6,0x26483505,0x378b2e46,0x3bff3b99,0x34a53913,0xb848b444,0x3ba83a2f,0x3ac23bb6,0xb3c6aa48,0xbbf1bbff,0x3bc33bfe,0xafd6a648,
0xb8c4b6d7,0xbb99bbce,0x3a6d3b3b,0xb505b303,0xbaddb9ed,0xbaf6bb50,0x381d395f,0xb7e3b67c,0xbbeabb88,0xba0fba8a,0x30b23564,0xb93ab89b,
0x3c003c00,0xba4fb9cb,0,0xb8ecb984,0x3c003c00,0xbb25bac2,0,0xb732b848,0x3c003c00,0xbbb6bb77,0,0xb444b5c2,
0x3c003c00,0xbbfabbe2,0,0xacb5b179,0x33c62a48,0x367c393a,0x3bc33bfe,0xbb50ba0f,0x38c436d7,0xb1792fd6,0x3a6d3b3b,0xbbe2bbf1,
0x3add39ed,0xb984b732,0x381d395f,0xb9cbbb25,0x3bea3b88,0xbbcebaf6,0x30b23564,0xb303b7e3,0xbb0ebbf6,0x3be23a4f,0x378b2e46,0x317938ec,
0xb4a5b913,0x39843b99,0x3ba83a2f,0xb9cbb505,0x378b2e46,0xb3033444,0x3b0e3bf6,0xbbcebbb6,0x3ba83a2f,0xbb77b93a,0x34a53913,0xb5c2ba0f,
0xb95fb0b2,0x2cb5b89b,0xb9edbbea,0x3bfa3a8a,0xbb88bbc3,0x3bf13984,0x3564b3c6,0x2fd639cb,0xaa48b8c4,0x35053ac2,0x3bfe3a6d,0xbb99b848,
0x3b3b381d,0xbaf6b5c2,0x36d73add,0xb7e3bb77,0x38723bd9,0xbb99bac2,0xbaa7b23e,0x3505b848,0xbaa7b23e,0x37e3b5c2,0xb872bbd9,0x3af63b77,
0xb872bbd9,0x3a0f3be2,0x3aa7323e,0xb93a3179,0x3aa7323e,0xba4fa648,0x38723bd9,0xb8ecbbff,0x3b8833c6,0xb84837e3,0x35643bc3,0xbac2baf6,
0xaa483a6d,0xb67cbbfa,0xbbfeb8c4,0x3b502cb5,0xbb3bbadd,0x3be238ec,0x36d7b81d,0xb1793a4f,0x39edb0b2,0xb9843505,0x395f3bea,0xb9cbbb99,
0xae46bba8,0x39843b25,0x3bf634a5,0xb9cb3732,0x3a2f3b0e,0xbbceb7e3,0xb913378b,0x3303baf6,0xbbf6b4a5,0x3b77acb5,0xae46bba8,0x35c23bfa,
0x3913b78b,0xb89b38ec,0x3a2f3b0e,0xba8aba4f,0xbbeab564,0x3af6b67c,0x30b2bb88,0x37e33b50,0x3bc3aa48,0xba0f389b,0x33c63bfe,0xb93aba8a,
0xba6d36d7,0x38ecb9cb,0xb8c4bb3b,0x3a4f3984,0x381db9ed,0xb7323ac2,0x3add395f,0xbb25b848,0xb61f3b64,0xb444bb77,0xbb64b61f,0x3bb6b5c2,
0x361fbb64,0x2cb53be2,0x3b64361f,0xbbfa3179,0xb61f3b64,0x2fd6bbff,0xbb64b61f,0x3bf12648,0x361fbb64,0xb5053bce,0x3b64361f,0xbb99b303,
0x3a6d36d7,0xbbff3505,0xb8c43b3b,0xa648bb99,0xb81db9ed,0x3ac23444,0x3addb95f,0xb8483bb6,0x30b23b88,0xb67cba0f,0xbbea3564,0x3b50b93a,
0x33c6bbfe,0xb1793bf1,0x3bc32a48,0xbbe22fd6,0x3a2fbb0e,0xb3033bb6,0x3913378b,0xbbce3444,0xbbf634a5,0x3b77ba0f,0x2e46bba8,0x35c2393a,
0x3913378b,0xba8aafd6,0xba2f3b0e,0x389bbbf1,0x2e46bba8,0xa6483b25,0x3bf6b4a5,0xbbff3732,0xb6d7b81d,0x3b25b303,0x3b3bbadd,0xb7323bce,
0xb95f3bea,0x3444bb50,0xb9edb0b2,0x3bb6b67c,0x3b88b3c6,0xbbfa389b,0xb5643bc3,0x2cb5ba8a,0xaa48ba6d,0x2fd63984,0x3bfeb8c4,0xbbf139cb,
0xbbd93aa7,0x393abbe2,0xb23eb872,0x3a0fb179,0x323e3872,0xb8eca648,0xbbd93aa7,0x3a4fbbff,0x3bd9baa7,0xbb253bce,0x323e3872,0xb732b303,
0xb23eb872,0x3444367c,0x3bd9baa7,0xbbb63b50,0xaa4838c4,0xb89b2fd6,0xbbfe3a6d,0x3a8abbf1,0x3b3bb81d,0xbbff3b25,0xb6d73add,0xa648b732,
0x39edbbea,0xb8483af6,0x395fb0b2,0xbac237e3,0xb564b3c6,0x367c2cb5,0x3b88bbc3,0xbb503bfa,0x3ba8ba2f,0xbb773bfa,0xb4a53913,0xb5c22cb5,
0x3b0ebbf6,0xb89b3a4f,0x378bae46,0xba8a38ec,0x34a5b913,0xa6483505,0x3ba8ba2f,0xbbff3b99,0xb78b2e46,0x3848b444,0x3b0ebbf6,0xbac23bb6,
0x381db95f,0x2fd6a648,0x3addb9ed,0xbbf13bff,0x30b2b564,0x3505b303,0x3beabb88,0xbb993bce,0xb3c62a48,0x37e3b67c,0x3bc3bbfe,0xbaf63b50,
0xb8c436d7,0x393ab89b,0x3a6dbb3b,0xba0f3a8a,0xb9a839a8,0x3bf1bbff,0x39a8b9a8,0xafd62648,0xb9a839a8,0x3b99bbce,0x39a8b9a8,0xb5053303,
0xb9a839a8,0x3af6bb50,0x39a8b9a8,0xb7e3367c,0xb9a839a8,0x3a0fba8a,0x39a8b9a8,0xb93a389b,0xbadd39ed,0x35c2acb5,0xb81d395f,0x3b77bbfa,
0xbbea3b88,0x3a8ab8ec,0xb0b23564,0x389bba4f,0xbbc33bfe,0x3bffbb99,0x33c6aa48,0x2648b505,0xba6d3b3b,0x3ac2bbb6,0x38c4b6d7,0xb8483444,
0x34a5b913,0xba8a3bf1,0xbba83a2f,0x389bafd6,0xb78b2e46,0x26483732,0xbb0e3bf6,0x3bffbb25,0xbba83a2f,0x3ac2b7e3,0xb4a53913,0x3848baf6,
0xbb0e3bf6,0x3b50bbfa,0x378bae46,0xb67cacb5,0x3bfeba6d,0xba0f3179,0x2a48b8c4,0xb93a3be2,0x36d7badd,0xba4f3bff,0xbb3b381d,0x38ec2648,
0xb95f30b2,0x37323303,0xb9ed3bea,0x3b25bbce,0xbb883bc3,0x3bb6bb50,0x356433c6,0xb444b67c,0x323e3872,0x3732bbce,0x3bd9baa7,0xbb253303,
0x3bd9baa7,0xbbb6367c,0xb23eb872,0xb4443b50,0xb23eb872,0xacb53a8a,0xbbd93aa7,0x3bfab89b,0xbbd93aa7,0x3bf1b9cb,0x323e3872,0xafd6b984,
0xbb3b3add,0x3bceb444,0x36d7381d,0x3303bbb6,0x39ed30b2,0xb5c2b93a,0x395fbbea,0xbb773a0f,0x3564bbc3,0xb89b3bf1,0xbb8833c6,0x3a8a2fd6,
0xbbfe38c4,0x3bffb732,0x2a483a6d,0x2648bb25,0xb913b78b,0x26483b99,0xba2f3b0e,0x3bffb505,0xae463ba8,0x3848bbb6,0x3bf6b4a5,0xbac2b444,
0x3a2fbb0e,0xbb50393a,0xb913b78b,0x367c3a0f,0xbbf634a5,0x3be2afd6,0xae463ba8,0x3179bbf1,0x38c4bb3b,0xbbb635c2,0xba6db6d7,0x34443b77,
0xbadd395f,0x3bfab179,0x381d39ed,0xacb5bbe2,0x3beab564,0xbbf1a648,0xb0b2bb88,0xafd63bff,0xbbc3aa48,0x3b993303,0xb3c63bfe,0x3505bbce,
0x3b64361f,0xb7e3bb50,0x361fbb64,0xbaf6367c,0xbb64b61f,0x393a3a8a,0xb61f3b64,0x3a0fb89b,0x3b64361f,0xba4fb984,0x361fbb64,0xb8ec39cb,
0xbb64b61f,0x3b253848,0xb61f3b64,0x3732bac2,0xb0b23b88,0x39cbb732,0x3bea3564,0xb984bb25,0xb3c6bbfe,0xb3033af6,0xbbc32a48,0x3bce37e3,
0x38c43b3b,0xb5c2bbfa,0x3a6db6d7,0xbb772cb5,0xbaddb95f,0x3a8a3a4f,0xb81d39ed,0x389bb8ec,0xbbf6b4a5,0x3ac23af6,0x2e463ba8,0x3848b7e3,
0x3913b78b,0xbb50acb5,0xba2fbb0e,0x367c3bfa,0x2e463ba8,0x3179ba4f,0x3bf634a5,0xbbe2b8ec,0xba2fbb0e,0x39cb3b99,0xb913378b,0x3984b505,
0xb564bbc3,0xb5053848,0xbb88b3c6,0x3b993ac2,0x3bfe38c4,0xbaf6bb77,0x2a48ba6d,0xb7e335c2,0xb6d7381d,0x393ab179,0x3b3b3add,0xba0fbbe2,
0xb95fbbea,0x38ec3bff,0xb9ed30b2,0x3a4f2648,0x3aa7323e,0xbbfaba8a,0xb872bbd9,0xacb5389b,0x38723bd9,0xafd6b9cb,0x3aa7323e,0xbbf1b984,
0xbaa7b23e,0x3b993848,0x38723bd9,0xb505bac2,0xb872bbd9,0x37e33b77,0xbaa7b23e,0x3af635c2,0x39ed3bea,0xb179b8ec,0x395f30b2,0xbbe2ba4f,
0xb56433c6,0x39cb3505,0x3b883bc3,0xb984bb99,0xbbfeba6d,0x3bce3bb6,0x2a4838c4,0x3303b444,0xb6d7badd,0x35c23a0f,0xbb3bb81d,0x3b77393a,
0xb78bae46,0x3b503a0f,0x3b0e3bf6,0xb67cb93a,0xbba8ba2f,0x3be23bf1,0x34a53913,0x3179afd6,0xbb0ebbf6,0x39cb3b25,0xb78bae46,0x39843732,
0xb4a5b913,0x330337e3,0xbba8ba2f,0x3bce3af6,0xbbc3bbfe,0x38ec3984,0xb3c6aa48,0x3a4f39cb,0xba6dbb3b,0x37323848,0xb8c4b6d7,0x3b253ac2,
0xb81db95f,0x344435c2,0xbaddb9ed,0x3bb63b77,0xb0b2b564,0x2cb53179,0xbbeabb88,0x3bfa3be2,0x3c003c00,0x3a4f39cb,0,0x38ec3984,
0x3c003c00,0x3b253ac2,0,0x37323848,0x3c003c00,0x3bb63b77,0,0x344435c2,0x3c003c00,0x3bfa3be2,0,0x2cb53179,
0x33c62a48,0xb67cb93a,0x3bc33bfe,0x3b503a0f,0x38c436d7,0x3179afd6,0x3a6d3b3b,0x3be23bf1,0x3add39ed,0x39843732,0x381d395f,0x39cb3b25,
0x3bea3b88,0x3bce3af6,0x30b23564,0x330337e3,0xbb0ebbf6,0xbbe2ba4f,0x378b2e46,0xb179b8ec,0xb4a5b913,0xb984bb99,0x3ba83a2f,0x39cb3505,
0x378b2e46,0x3303b444,0x3b0e3bf6,0x3bce3bb6,0x3ba83a2f,0x3b77393a,0x34a53913,0x35c23a0f,0xb95fb0b2,0xacb5389b,0xb9edbbea,0xbbfaba8a,
0xbb88bbc3,0xbbf1b984,0x3564b3c6,0xafd6b9cb,0xaa48b8c4,0xb505bac2,0x3bfe3a6d,0x3b993848,0x3b3b381d,0x3af635c2,0x36d73add,0x37e33b77,
0x38723bd9,0x3b993ac2,0xbaa7b23e,0xb5053848,0xbaa7b23e,0xb7e335c2,0xb872bbd9,0xbaf6bb77,0xb872bbd9,0xba0fbbe2,0x3aa7323e,0x393ab179,
0x3aa7323e,0x3a4f2648,0x38723bd9,0x38ec3bff,0x3b8833c6,0x3848b7e3,0x35643bc3,0x3ac23af6,0xaa483a6d,0x367c3bfa,0xbbfeb8c4,0xbb50acb5,
0xbb3bbadd,0xbbe2b8ec,0x36d7b81d,0x3179ba4f,0x39edb0b2,0x3984b505,0x395f3bea,0x39cb3b99,0xae46bba8,0xb984bb25,0x3bf634a5,0x39cbb732,
0x3a2f3b0e,0x3bce37e3,0xb913378b,0xb3033af6,0xbbf6b4a5,0xbb772cb5,0xae46bba8,0xb5c2bbfa,0x3913b78b,0x389bb8ec,0x3a2f3b0e,0x3a8a3a4f,
0xbbeab564,0xbaf6367c,0x30b2bb88,0xb7e3bb50,0x3bc3aa48,0x3a0fb89b,0x33c63bfe,0x393a3a8a,0xba6d36d7,0xb8ec39cb,0xb8c4bb3b,0xba4fb984,
0x381db9ed,0x3732bac2,0x3add395f,0x3b253848,0xb61f3b64,0x34443b77,0xbb64b61f,0xbbb635c2,0x361fbb64,0xacb5bbe2,0x3b64361f,0x3bfab179,
0xb61f3b64,0xafd63bff,0xbb64b61f,0xbbf1a648,0x361fbb64,0x3505bbce,0x3b64361f,0x3b993303,0x3a6d36d7,0x3bffb505,0xb8c43b3b,0x26483b99,
0xb81db9ed,0xbac2b444,0x3addb95f,0x3848bbb6,0x30b23b88,0x367c3a0f,0xbbea3564,0xbb50393a,0x33c6bbfe,0x3179bbf1,0x3bc32a48,0x3be2afd6,
0x3a2fbb0e,0x3303bbb6,0x3913378b,0x3bceb444,0xbbf634a5,0xbb773a0f,0x2e46bba8,0xb5c2b93a,0x3913378b,0x3a8a2fd6,0xba2f3b0e,0xb89b3bf1,
0x2e46bba8,0x2648bb25,0x3bf6b4a5,0x3bffb732,0xb6d7b81d,0xbb253303,0x3b3bbadd,0x3732bbce,0xb95f3bea,0xb4443b50,0xb9edb0b2,0xbbb6367c,
0x3b88b3c6,0x3bfab89b,0xb5643bc3,0xacb53a8a,0xaa48ba6d,0xafd6b984,0x3bfeb8c4,0x3bf1b9cb,0xbbd93aa7,0xb93a3be2,0xb23eb872,0xba0f3179,
0x323e3872,0x38ec2648,0xbbd93aa7,0xba4f3bff,0x3bd9baa7,0x3b25bbce,0x323e3872,0x37323303,0xb23eb872,0xb444b67c,0x3bd9baa7,0x3bb6bb50,
0xaa4838c4,0x389bafd6,0xbbfe3a6d,0xba8a3bf1,0x3b3bb81d,0x3bffbb25,0xb6d73add,0x26483732,0x39edbbea,0x3848baf6,0x395fb0b2,0x3ac2b7e3,
0xb564b3c6,0xb67cacb5,0x3b88bbc3,0x3b50bbfa,0x3ba8ba2f,0x3b77bbfa,0xb4a53913,0x35c2acb5,0x3b0ebbf6,0x389bba4f,0x378bae46,0x3a8ab8ec,
0x34a5b913,0x2648b505,0x3ba8ba2f,0x3bffbb99,0xb78b2e46,0xb8483444,0x3b0ebbf6,0x3ac2bbb6,0x381db95f,0xafd62648,0x3addb9ed,0x3bf1bbff,
0x30b2b564,0xb5053303,0x3beabb88,0x3b99bbce,0xb3c62a48,0xb7e3367c,0x3bc3bbfe,0x3af6bb50,0xb8c436d7,0xb93a389b,0x3a6dbb3b,0x3a0fba8a,
0xb9a839a8,0xbbf13bff,0x39a8b9a8,0x2fd6a648,0xb9a839a8,0xbb993bce,0x39a8b9a8,0x3505b303,0xb9a839a8,0xbaf63b50,0x39a8b9a8,0x37e3b67c,
0xb9a839a8,0xba0f3a8a,0x39a8b9a8,0x393ab89b,0xbadd39ed,0xb5c22cb5,0xb81d395f,0xbb773bfa,0xbbea3b88,0xba8a38ec,0xb0b23564,0xb89b3a4f,
0xbbc33bfe,0xbbff3b99,0x33c6aa48,0xa6483505,0xba6d3b3b,0xbac23bb6,0x38c4b6d7,0x3848b444,0x34a5b913,0x3a8abbf1,0xbba83a2f,0xb89b2fd6,
0xb78b2e46,0xa648b732,0xbb0e3bf6,0xbbff3b25,0xbba83a2f,0xbac237e3,0xb4a53913,0xb8483af6,0xbb0e3bf6,0xbb503bfa,0x378bae46,0x367c2cb5,
0x3bfeba6d,0x3a0fb179,0x2a48b8c4,0x393abbe2,0x36d7badd,0x3a4fbbff,0xbb3b381d,0xb8eca648,0xb95f30b2,0xb732b303,0xb9ed3bea,0xbb253bce,
0xbb883bc3,0xbbb63b50,0x356433c6,0x3444367c,0x323e3872,0xb7323bce,0x3bd9baa7,0x3b25b303,0x3bd9baa7,0x3bb6b67c,0xb23eb872,0x3444bb50,
0xb23eb872,0x2cb5ba8a,0xbbd93aa7,0xbbfa389b,0xbbd93aa7,0xbbf139cb,0x323e3872,0x2fd63984,0xbb3b3add,0xbbce3444,0x36d7381d,0xb3033bb6,
0x39ed30b2,0x35c2393a,0x395fbbea,0x3b77ba0f,0x3564bbc3,0x389bbbf1,0xbb8833c6,0xba8aafd6,0xbbfe38c4,0xbbff3732,0x2a483a6d,0xa6483b25,
0xb913b78b,0xa648bb99,0xba2f3b0e,0xbbff3505,0xae463ba8,0xb8483bb6,0x3bf6b4a5,0x3ac23444,0x3a2fbb0e,0x3b50b93a,0xb913b78b,0xb67cba0f,
0xbbf634a5,0xbbe22fd6,0xae463ba8,0xb1793bf1,0x38c4bb3b,0x3bb6b5c2,0xba6db6d7,0xb444bb77,0xbadd395f,0xbbfa3179,0x381d39ed,0x2cb53be2,
0x3beab564,0x3bf12648,0xb0b2bb88,0x2fd6bbff,0xbbc3aa48,0xbb99b303,0xb3c63bfe,0xb5053bce,0x3b64361f,0x37e33b50,0x361fbb64,0x3af6b67c,
0xbb64b61f,0xb93aba8a,0xb61f3b64,0xba0f389b,0x3b64361f,0x3a4f3984,0x361fbb64,0x38ecb9cb,0xbb64b61f,0xbb25b848,0xb61f3b64,0xb7323ac2,
0xb0b23b88,0xb9cb3732,0x3bea3564,0x39843b25,0xb3c6bbfe,0x3303baf6,0xbbc32a48,0xbbceb7e3,0x38c43b3b,0x35c23bfa,0x3a6db6d7,0x3b77acb5,
0xbaddb95f,0xba8aba4f,0xb81d39ed,0xb89b38ec,0xbbf6b4a5,0xbac2baf6,0x2e463ba8,0xb84837e3,0x3913b78b,0x3b502cb5,0xba2fbb0e,0xb67cbbfa,
0x2e463ba8,0xb1793a4f,0x3bf634a5,0x3be238ec,0xba2fbb0e,0xb9cbbb99,0xb913378b,0xb9843505,0xb564bbc3,0x3505b848,0xbb88b3c6,0xbb99bac2,
0x3bfe38c4,0x3af63b77,0x2a48ba6d,0x37e3b5c2,0xb6d7381d,0xb93a3179,0x3b3b3add,0x3a0f3be2,0xb95fbbea,0xb8ecbbff,0xb9ed30b2,0xba4fa648,
0x3aa7323e,0x3bfa3a8a,0xb872bbd9,0x2cb5b89b,0x38723bd9,0x2fd639cb,0x3aa7323e,0x3bf13984,0xbaa7b23e,0xbb99b848,0x38723bd9,0x35053ac2,
0xb872bbd9,0xb7e3bb77,0xbaa7b23e,0xbaf6b5c2,0x39ed3bea,0x317938ec,0x395f30b2,0x3be23a4f,0xb56433c6,0xb9cbb505,0x3b883bc3,0x39843b99,
0xbbfeba6d,0xbbcebbb6,0x2a4838c4,0xb3033444,0xb6d7badd,0xb5c2ba0f,0xbb3bb81d,0xbb77b93a,0xb78bae46,0xbb50ba0f,0x3b0e3bf6,0x367c393a,
0xbba8ba2f,0xbbe2bbf1,0x34a53913,0xb1792fd6,0xbb0ebbf6,0xb9cbbb25,0xb78bae46,0xb984b732,0xb4a5b913,0xb303b7e3,0xbba8ba2f,0xbbcebaf6,
0xbbc3bbfe,0xb8ecb984,0xb3c6aa48,0xba4fb9cb,0xba6dbb3b,0xb732b848,0xb8c4b6d7,0xbb25bac2,0xb81db95f,0xb444b5c2,0xbaddb9ed,0xbbb6bb77,
0xb0b2b564,0xacb5b179,0xbbeabb88,0xbbfabbe2,0x3c003c00,0x96480000,0x3c003c00,0xa311a248,0x3c003c00,0x9cb69a48,0x3c003c00,0xa452a3db,
0x3c003c00,0x9fdb9e48,0x3c003c00,0xa51ba4b6,0x3c003c00,0xa17fa0b6,0x3bff3c00,0xa5e4a57f,0x3c003c00,0x9fdb0000,0x3bfb3bfc,0xac6aabd9,
0x3bff3c00,0xa5e4a3db,0x3bf93bfa,0xad65ace7,0x3bfe3bff,0xa8e8a7da,0x3bf63bf7,0xae5fade2,0x3bfd3bfe,0xaadea9e3,0x3bf23bf4,0xaf59aedc,
0x3c003c00,0xa3110000,0x3bf03bf4,0xafefaf0e,0x3bfe3bff,0xa94da711,0x3be83bed,0xb0d7b067,0x3bfb3bfd,0xac6aab11,0x3bdf3be4,0xb1b6b147,
0x3bf63bf9,0xae2dad4c,0x3bd43bda,0xb294b226,0x3c003c00,0xa51b0000,0x3bdf3be6,0xb1b6b115,0x3bfc3bfe,0xaba7a91b,0x3bcf3bd7,0xb2f7b257,
0x3bf63bf9,0xae5fad1a,0x3bbc3bc6,0xb41ab396,0x3bec3bf1,0xb074afa4,0x3ba53bb1,0xb4b7b469,0x3bff3c00,0xa6ad0000,0x3bc83bd4,0xb371b2a1,
0x3bfa3bfd,0xad00aaac,0x3bac3bbb,0xb487b420,0x3bef3bf5,0xb029aeaa,0x3b8b3b9d,0xb552b4ed,0x3bde3be7,0xb1cfb0fd,0x3b653b79,0xb61ab5b6,
0x3bff3c00,0xa81f0000,0x3bab3bbc,0xb493b414,0x3bf63bfc,0xae2dac1f,0x3b813b97,0xb58db511,0x3be53bef,0xb122b01d,0x3b4f3b69,0xb682b608,
0x3bcc3bda,0xb328b226,0x3b163b33,0xb76fb6f9,0x3bfe3c00,0xa8e80000,0x3b873ba0,0xb56ab4d5,0x3bf23bfa,0xaf59ace7,0x3b4c3b6b,0xb68db5fd,
0x3bda3be8,0xb219b0e4,0x3b073b2b,0xb7a6b71b,0x3bb73bca,0xb43eb34c,0x3ab63ae0,0xb85ab817,0x3bfe3c00,0xa9b10000,0x3b5e3b80,0xb63cb593,
0x3bee3bf8,0xb042adb0,0x3b103b39,0xb785b6e3,0x3bce3be0,0xb30fb1aa,0x3ab33ae3,0xb85fb812,0x3b9e3bb7,0xb4e7b438,0x3a493a7f,0xb8f3b8ab,
0x3bfd3c00,0xaa7a0000,0x3b2f3b5a,0xb70ab64e,0x3be83bf6,0xb0d7ae78,0x3acb3aff,0xb83ab7c2,0x3bbf3bd6,0xb402b26f,0x3a543a92,0xb8e5b891,
0x3b813ba2,0xb58db4c9,0x39cd3a13,0xb982b935,0x3bfd3c00,0xab430000,0x3afb3b30,0xb7d2b705,0x3be23bf3,0xb16caf40,0x3a7e3abf,0xb8adb84d,
0x3bae3bcb,0xb47bb334,0x39eb3a37,0xb962b909,0x3b603b8a,0xb631b558,0x3946399b,0xba04b9b5,0x3bfc3c00,0xac060000,0x3ac13b02,0xb84ab7b7,
0x3bdc3bf0,0xb201b004,0x3a293a78,0xb91bb8b5,0x3b9c3bc0,0xb4f3b3f7,0x397939d4,0xb9d6b97b,0x3b3d3b70,0xb6d2b5e5,0x38b23918,0xba7aba2b,
0x3bfb3c00,0xac6a0000,0x3a813ad0,0xb8a8b832,0x3bd43bed,0xb294b067,0x39cd3a2b,0xb982b918,0x3b873bb2,0xb56ab45d,0x38fd3969,0xba41b9e5,
0x3b163b53,0xb76fb670,0x3815388c,0xbae1ba95,0x3bfa3c00,0xacce0000,0x3a3d3a99,0xb902b887,0x3bcc3be9,0xb328b0cb,0x396b39d8,0xb9e3b976,
0x3b713ba4,0xb5dfb4bd,0x387a38f6,0xbaa2ba47,0x3aeb3b33,0xb805b6f9,0x36dd37ee,0xbb3abaf3,0x3bf93c00,0xad330000,0x39f43a5e,0xb958b8d8,
0x3bc33be5,0xb3bab12e,0x39023980,0xba3db9d0,0x3b593b95,0xb654b51d,0x37dd387c,0xbaf7baa0,0x3abd3b11,0xb850b780,0x358136b5,0xbb83bb43,
0x3bf83c00,0xad970000,0x39a63a1f,0xb9aab927,0x3bba3be1,0xb426b191,0x38943922,0xba90ba23,0x3b3f3b84,0xb6c6b57c,0x36bb37f9,0xbb42baf0,
0x3a8c3aed,0xb899b802,0x341a3570,0xbbbcbb86,0x3bf73c00,0xadfb0000,0x395439dc,0xb9f8b972,0x3bb03bdc,0xb46fb1f4,0x382038bf,0xbadbba71,
0x3b243b72,0xb737b5da,0x358d36ee,0xbb81bb36,0x3a583ac6,0xb8e0b842,0x31533420,0xbbe3bbbb,0x3bf63c00,0xae5f0000,0x38fd3996,0xba41b9ba,
0x3ba53bd7,0xb4b7b257,0x374e3858,0xbb1ebab8,0x3b073b5f,0xb7a6b637,0x345735da,0xbbb3bb72,0x3a213a9c,0xb924b881,0x2cce3191,0xbbfabbe1,
0x3bf53c00,0xaec30000,0x38a3394d,0xba85b9fe,0x3b9a3bd2,0xb4ffb2b9,0x365437d8,0xbb59baf9,0x3ae83b4b,0xb80ab693,0x323234bd,0xbbd9bba4,
0x39e73a71,0xb966b8bf,0xa4522db0,0xbc00bbf8,0x3bf33c00,0xaf270000,0x38453900,0xbac4ba3f,0x3b8e3bcd,0xb546b31b,0x355236f9,0xbb8bbb33,
0x3ac73b36,0xb840b6ee,0x2f593334,0xbbf2bbcb,0x39aa3a43,0xb9a6b8fb,0xaef51a48,0xbbf4bc00,0x3bf23c00,0xaf8b0000,0x37c838b0,0xbafeba7c,
0x3b813bc7,0xb58db37d,0x344b3614,0xbbb5bb67,0x3aa53b20,0xb874b748,0x288430e4,0xbbffbbe8,0x396b3a13,0xb9e3b935,0xb263ad4c,0xbbd7bbf9,
0x3bf03c00,0xafef0000,0x36ff385d,0xbb32bab5,0x3b733bc1,0xb5d4b3df,0x327c3529,0xbbd6bb93,0x3a813b08,0xb8a8b7a1,0xa9b12d1a,0xbbfebbf9,
0x392939e1,0xba1db96d,0xb49fb160,0xbba9bbe3,0x3bef3c00,0xb0290000,0x36313807,0xbb60bae9,0x3b653bbb,0xb61ab420,0x305b3438,0xbbedbbb7,
0x3a5c3af0,0xb8dbb7f9,0xafef1e48,0xbbf0bc00,0x38e539ad,0xba54b9a4,0xb602b408,0xbb6abbbe,0x3bed3c00,0xb05b0000,0x355e375e,0xbb89bb1a,
0x3b573bb4,0xb65fb451,0x2c6a3288,0xbbfbbbd5,0x3a353ad6,0xb90cb828,0xb27cac51,0xbbd6bbfb,0x389e3976,0xba89b9d8,0xb759b558,0xbb1bbb8a,
0x3beb3c00,0xb08d0000,0x348736aa,0xbbacbb46,0x3b473bad,0xb6a4b481,0x16483099,0xbc00bbeb,0x3a0d3abc,0xb93cb852,0xb47bb080,0xbbaebbec,
0x3855393e,0xbababa0b,0xb850b69e,0xbabdbb49,0x3be93c00,0xb0be0000,0x335935f1,0xbbc9bb6e,0x3b373ba6,0xb6e8b4b1,0xac382d4c,0xbbfcbbf9,
0x39e33aa0,0xb96bb87c,0xb5b1b2d2,0xbb7abbd1,0x380a3905,0xbae8ba3b,0xb8eab7d8,0xba50baf9,0x3be73c00,0xb0f00000,0x319e3534,0xbbe0bb91,
0x3b273b9e,0xb72cb4e1,0xb042257f,0xbbeebc00,0x39b83a83,0xb999b8a6,0xb6ddb48d,0xbb3abbab,0x377a38c9,0xbb13ba69,0xb979b881,0xb9d6ba9c,
0x3be53c00,0xb1220000,0x2fbd3475,0xbbf1bbaf,0x3b163b97,0xb76fb511,0xb263a91b,0xbbd7bbfe,0x398b3a65,0xb9c5b8ce,0xb7feb5ab,0xbaeebb7b,
0x36dd388c,0xbb3aba95,0xb9fcb90e,0xb94fba33,0x3be33c00,0xb1530000,0x2c383365,0xbbfcbbc9,0x3b043b8f,0xb7b2b540,0xb43eae78,0xbbb7bbf6,
0x395d3a47,0xb9f0b8f6,0xb889b6c1,0xba97bb41,0x363c384d,0xbb5ebabf,0xba73b992,0xb8bcb9be,0x3be13c00,0xb1850000,0x217f31db,0xbc00bbdd,
0x3af13b86,0xb7f3b570,0xb546b12e,0xbb8ebbe5,0x392e3a27,0xba19b91d,0xb90cb7cd,0xba35bafc,0x3599380d,0xbb7fbae6,0xbadbba0b,0xb820b93e,
0x3bdf3c00,0xb1b60000,0xa9b1304e,0xbbfebbed,0x3ade3b7d,0xb81ab59f,0xb648b31b,0xbb5cbbcd,0x38fd3a07,0xba41b943,0xb986b867,0xb9c9baae,
0x34f33796,0xbb9cbb0b,0xbb35ba78,0xb6f4b8b5,0x3bdd3c00,0xb1e80000,0xae5f2d7e,0xbbf6bbf8,0x3acb3b74,0xb83ab5ce,0xb742b481,0xbb21bbad,
0x38cc39e5,0xba67b969,0xb9f8b8e2,0xb954ba56,0x344b3710,0xbbb5bb2e,0xbb7fbad9,0xb599b822,0x3bda3c00,0xb2190000,0xb0f028b6,0xbbe7bbff,
0x3ab63b6b,0xb85ab5fd,0xb81ab570,0xbadebb86,0x389939c3,0xba8cb98d,0xba60b956,0xb8d6b9f6,0x33403687,0xbbcbbb4e,0xbbb8bb2e,0xb432b710,
0x3bff3bff,0xa6ada648,0x3bfe3bff,0xa8e8a8b6,0x3bff3bff,0xa776a711,0x3bfe3bfe,0xa94da91b,0x3bff3bff,0xa81fa7da,0x3bfe3bfe,0xa9b1a97f,
0x3bff3bff,0xa884a852,0x3bfe3bfe,0xaa16a9e3,0x3bef3bf1,0xb029afd6,0x3bda3bdd,0xb219b1db,0x3bea3bed,0xb0a6b067,0x3bd43bd7,0xb294b257,
0x3be53be8,0xb122b0e4,0x3bce3bd1,0xb30fb2d2,0x3be03be3,0xb19eb160,0x3bc63bca,0xb389b34c,0x3bc83bce,0xb371b303,0x3b873b91,0xb56ab534,
0x3bba3bc1,0xb426b3df,0x3b733b7d,0xb5d4b59f,0x3bab3bb2,0xb493b45d,0x3b5e3b69,0xb63cb608,0x3b9a3ba2,0xb4ffb4c9,0x3b473b53,0xb6a4b670,
0x3b8b3b99,0xb552b505,0x3b073b1a,0xb7a6b75e,0x3b6f3b7d,0xb5ebb59f,0x3ade3af3,0xb81ab7ee,0x3b4f3b5f,0xb682b637,0x3ab33ac9,0xb85fb83d,
0x3b2c3b3e,0xb715b6cc,0x3a853a9c,0xb8a3b881,0x3b3a3b50,0xb6ddb67c,0x3a5c3a7c,0xb8dbb8b0,0x3b0a3b22,0xb79bb73d,0x3a193a3b,0xb92eb905,
0x3ad53af0,0xb82ab7f9,0x39d239f6,0xb97db956,0x3a9b3ab8,0xb884b858,0x398639ad,0xb9c9b9a4,0x3ad53af6,0xb82ab7e3,0x398b39ba,0xb9c5b996,
0x3a8c3ab1,0xb899b862,0x3929395b,0xba1db9f2,0x3a3d3a65,0xb902b8ce,0x38c138f6,0xba6fba47,0x39e73a13,0xb966b935,0x3855388c,0xbababa95,
0x3a5c3a8a,0xb8dbb89b,0x389938d8,0xba8cba5e,0x39f83a2b,0xb954b918,0x38153858,0xbae1bab8,0x398b39c3,0xb9c5b98d,0x371537a1,0xbb2cbb08,
0x39163951,0xba2db9fa,0x35f73687,0xbb6cbb4e,0x39d23a0f,0xb97db93a,0x371537b7,0xbb2cbb02,0x394f3992,0xb9fcb9be,0x35c83670,0xbb76bb53,
0x38c13909,0xba6fba37,0x346f351d,0xbbb0bb95,0x382a3877,0xbad5baa3,0x3219337d,0xbbdabbc7,0x39373984,0xba11b9cb,0x34cf3593,0xbba1bb80,
0x389438e7,0xba90ba52,0x327c3408,0xbbd6bbbe,0x37c8383d,0xbafebac9,0x2e9130e4,0xbbf5bbe8,0x36543710,0xbb59bb2e,0x16482aac,0xbc00bbfd,
0x388e38ec,0xba93ba4f,0x30d732a1,0xbbe8bbd4,0x3790382d,0xbb0dbad3,0x28e82e14,0xbbfebbf7,0x35eb36c1,0xbb6fbb41,0xaccea4b6,0xbbfabc00,
0x34323511,0xbbb8bb97,0xb201b036,0xbbdcbbee,0x37b23848,0xbb04bac2,0x96482bd9,0xbc00bbfc,0x35df36cc,0xbb71bb3e,0xb010ac1f,0xbbefbbfc,
0x33eb34ed,0xbbc0bb9d,0xb402b20d,0xbbbfbbdb,0x2fef31f4,0xbbf0bbdc,0xb5ebb4f9,0xbb6fbb9b,0x36313732,0xbb60bb25,0xb0f0ad7e,0xbbe7bbf8,
0x341a3529,0xbbbcbb93,0xb49fb31b,0xbba9bbcd,0x2fbd320d,0xbbf1bbdb,0xb6afb5ab,0xbb45bb7b,0xa4522aac,0xbc00bbfd,0xb850b7ac,0xbabdbb05,
0x349f35c2,0xbba9bb77,0xb4dbb365,0xbb9fbbc9,0x308d32ea,0xbbebbbd0,0xb715b5fd,0xbb2cbb6b,0x9fdb2c51,0xbc00bbfb,0xb894b812,0xba90bae3,
0xb109ad4c,0xbbe6bbf9,0xb982b90e,0xb9cdba33,0x32013444,0xbbdcbbb6,0xb721b5f1,0xbb2abb6e,0x26ad2edc,0xbbffbbf4,0xb8adb822,0xba7ebad9,
0xb05bab11,0xbbedbbfd,0xb9aab930,0xb9a6ba17,0xb4b7b2ea,0xbba5bbd0,0xba81ba1b,0xb8a8b92b,0x2d653179,0xbbf9bbe2,0xb89eb807,0xba89bae9,
0xadc99a48,0xbbf8bc00,0xb9afb92b,0xb9a1ba1b,0xb432b1aa,0xbbb8bbe0,0xba93ba27,0xb88eb91d,0xb6d2b587,0xbb3dbb82,0xbb45baf3,0xb6afb7ee,
0xa51b2cb5,0xbc00bbfa,0xb990b900,0xb9c0ba3f,0xb294af40,0xbbd4bbf3,0xba89ba13,0xb89eb935,0xb625b4bd,0xbb63bba4,0xbb47baf0,0xb6a4b7f9,
0xb865b780,0xbab0bb11,0xbbc5bb8f,0xb3a2b540,0xafefa648,0xbbf0bbff,0xba60b9dc,0xb8d6b972,0xb517b31b,0xbb96bbcd,0xbb35bad3,0xb6f4b82d,
0xb7feb693,0xbaeebb4b,0xbbc0bb84,0xb3ebb57c,0xb94ab8ab,0xba00ba7f,0xbbfdbbe9,0xaa7ab0cb,0xb340afd6,0xbbcbbbf1,0xbb0aba99,0xb79bb887,
0xb6d2b540,0xbb3dbb8f,0xbbaebb67,0xb47bb614,0xb8dbb828,0xba5cbad6,0xbbfbbbe0,0xac9cb1aa,0xba15b980,0xb933b9d0,0xbbecbbff,0x30742852,
0xb53ab303,0xbb90bbce,0xbb89bb30,0xb55eb705,0xb83ab6e3,0xbacbbb39,0xbbf2bbca,0xaf8bb34c,0xb9a1b8f6,0xb9afba47,0xbbf5bc00,0x2ec39e48,
0xbac1ba3b,0xb84ab905,0xbb92bbd0,0x352f32ea,0xb6c6b505,0xbb3fbb99,0xbbdcbba0,0xb201b4d5,0xb8fdb838,0xba41bacc,0xbbfebbfb,0x2a16ac83,
0xba50b9b1,0xb8eab99f,0xbbaebbe4,0x347b3147,0xbb4abad9,0xb699b822,0xbaf1bb5d,0x37f33642,0xb820b67c,0xbadbbb50,0xbbffbbe6,0xa884b115,
0xb9afb8f1,0xb9a1ba4b,0xbbd2bbf8,0x32c62db0,0xbae5ba56,0xb80fb8e2,0xbb2abb8c,0x3721354c,0xbbaebb58,0xb47bb659,0xba11baaa,0x3937386d,
0xb8d1b7e3,0xba64baf6,0xbbf2bc00,0x2f8ba248,0xba4db99b,0xb8eeb9b5,0xbb6fbbc1,0x35eb33df,0xbb5cbae3,0xb648b812,0xba6bbafc,0x38c737cd,
0xbbebbbb4,0xb08db451,0xb8f8b9be,0x3a453992,0xb974b89b,0xb9daba8a,0xbbb5bbed,0x344b304e,0xbad5ba33,0xb82ab90e,0xbad8bb58,0x38253659,
0xbbb3bb55,0xb457b665,0xb979ba37,0x39d63909,0xbc00bbed,0x9648b067,0xb764b8a0,0x3b183a87,0xba09b93a,0xb941ba0f,0xbb4abbaf,0x36993475,
0xbb45bab8,0xb6afb858,0xba11babf,0x3937384d,0xbbeabbab,0xb0a6b48d,0xb85ab943,0x3ab63a07,0xbbecbc00,0x30749a48,0xb493b6b5,0x3bab3b43,
0xba8cb9cb,0xb899b984,0xbab3bb46,0x385f36aa,0xbb9cbb28,0xb4f3b726,0xb91fb9fa,0x3a253951,0xbc00bbe4,0xa452b147,0xb631b828,0x3b603ad6,
0xbbb0bbee,0x346f3036,0xae5fb3df,0x3bf63bc1,0xbafeba4f,0xb7c8b8ec,0xb9f4bab5,0x3958385d,0xbbd8bb82,0xb24bb587,0xb80ab90e,0x3ae83a33,
0xbbf3bbfe,0x2f27a97f,0xb2f7b5da,0x3bcf3b72,0xbb4cbbb7,0x368d3438,0x2dc9ac1f,0x3bf83bfc,0xbb5cbac2,0xb648b848,0xb911b9fe,0x3a31394d,
0xbbf9bbc4,0xad33b3ae,0xb5b1b802,0x3b7a3aed,0xbbc5bbf9,0x33a22d1a,0xa94db26f,0x3bfe3bd6,0xbac4bb5d,0x38453642,0x346f2fa4,0x3bb03bf1,
0xbba5bb25,0xb4b7b732,0xb80fb927,0x3ae53a1f,0xbbffbbee,0x2884b036,0xb24bb5b6,0x3bd83b79,0xbb76bbd6,0x35c8326f,0x305ba7da,0x3bed3bff,
0xba19bae0,0x392e3817,0x374234c9,0x3b213ba2,0xbbd9bb77,0xb232b5c2,0xb5ebb832,0x3b6f3ad0,0xbbe8bc00,0x30d7a57f,0xa81fb288,0x3bff3bd5,
0xbb07bb95,0x37a6351d,0x34f33080,0x3b9c3bec,0xb94fba43,0x39fc38fb,0x38ea3780,0x3a503b11,0xbbf8bbb6,0xadc9b444,0xb328b64e,0x3bcc3b5a,
0xbbb7bbf8,0x343e2db0,0x3042a9e3,0x3bee3bfe,0xba7abb36,0x38b236ee,0x379034ed,0x3b0d3b9d,0xb86ab989,0x3aac39c7,0x3a0438fb,0x39463a43,
0xbc00bbe2,0x2311b179,0xac9cb414,0x3bfb3bbc,0xbb6abbd7,0x36023257,0x34b72f40,0x3ba53bf3,0xb9d2babc,0x397d3852,0x38f83775,0x3a453b14,
0xb6ddb8b5,0x3b3a3a78,0x3ae83a0b,0x380a393e,0xbbf2bbfa,0x2f8bacb5,0x2d33af0e,0x3bf93bf4,0xbb04bb9e,0x37b234e1,0x372c3451,0x3b273bb4,
0xb911ba27,0x3a31391d,0x3a0038e2,0x394a3a56,0xb4c3b796,0x3ba33b0b,0x3b8b3ae6,0x3552380d,0x4c004c00,0x26480000,0x4c004c00,0x33113248,
0x4c004c00,0x2cb62a48,0x4c004c00,0x345233db,0x4c004c00,0x2fdb2e48,0x4c004c00,0x351b34b6,0x4c004c00,0x317f30b6,0x4bff4c00,0x35e4357f,
0x4c004c00,0x2fdb0000,0x4bfb4bfc,0x3c6a3bd9,0x4bff4c00,0x35e433db,0x4bf94bfa,0x3d653ce7,0x4bfe4bff,0x38e837da,0x4bf64bf7,0x3e5f3de2,
0x4bfd4bfe,0x3ade39e3,0x4bf24bf4,0x3f593edc,0x4c004c00,0x33110000,0x4bf04bf4,0x3fef3f0e,0x4bfe4bff,0x394d3711,0x4be84bed,0x40d74067,
0x4bfb4bfd,0x3c6a3b11,0x4bdf4be4,0x41b64147,0x4bf64bf9,0x3e2d3d4c,0x4bd44bda,0x42944226,0x4c004c00,0x351b0000,0x4bdf4be6,0x41b64115,
0x4bfc4bfe,0x3ba7391b,0x4bcf4bd7,0x42f74257,0x4bf64bf9,0x3e5f3d1a,0x4bbc4bc6,0x441a4396,0x4bec4bf1,0x40743fa4,0x4ba54bb1,0x44b74469,
0x4bff4c00,0x36ad0000,0x4bc84bd4,0x437142a1,0x4bfa4bfd,0x3d003aac,0x4bac4bbb,0x44874420,0x4bef4bf5,0x40293eaa,0x4b8b4b9d,0x455244ed,
0x4bde4be7,0x41cf40fd,0x4b654b79,0x461a45b6,0x4bff4c00,0x381f0000,0x4bab4bbc,0x44934414,0x4bf64bfc,0x3e2d3c1f,0x4b814b97,0x458d4511,
0x4be54bef,0x4122401d,0x4b4f4b69,0x46824608,0x4bcc4bda,0x43284226,0x4b164b33,0x476f46f9,0x4bfe4c00,0x38e80000,0x4b874ba0,0x456a44d5,
0x4bf24bfa,0x3f593ce7,0x4b4c4b6b,0x468d45fd,0x4bda4be8,0x421940e4,0x4b074b2b,0x47a6471b,0x4bb74bca,0x443e434c,0x4ab64ae0,0x485a4817,
0x4bfe4c00,0x39b10000,0x4b5e4b80,0x463c4593,0x4bee4bf8,0x40423db0,0x4b104b39,0x478546e3,0x4bce4be0,0x430f41aa,0x4ab34ae3,0x485f4812,
0x4b9e4bb7,0x44e74438,0x4a494a7f,0x48f348ab,0x4bfd4c00,0x3a7a0000,0x4b2f4b5a,0x470a464e,0x4be84bf6,0x40d73e78,0x4acb4aff,0x483a47c2,
0x4bbf4bd6,0x4402426f,0x4a544a92,0x48e54891,0x4b814ba2,0x458d44c9,0x49cd4a13,0x49824935,0x4bfd4c00,0x3b430000,0x4afb4b30,0x47d24705,
0x4be24bf3,0x416c3f40,0x4a7e4abf,0x48ad484d,0x4bae4bcb,0x447b4334,0x49eb4a37,0x49624909,0x4b604b8a,0x46314558,0x4946499b,0x4a0449b5,
0x4bfc4c00,0x3c060000,0x4ac14b02,0x484a47b7,0x4bdc4bf0,0x42014004,0x4a294a78,0x491b48b5,0x4b9c4bc0,0x44f343f7,0x497949d4,0x49d6497b,
0x4b3d4b70,0x46d245e5,0x48b24918,0x4a7a4a2b,0x4bfb4c00,0x3c6a0000,0x4a814ad0,0x48a84832,0x4bd44bed,0x42944067,0x49cd4a2b,0x49824918,
0x4b874bb2,0x456a445d,0x48fd4969,0x4a4149e5,0x4b164b53,0x476f4670,0x4815488c,0x4ae14a95,0x4bfa4c00,0x3cce0000,0x4a3d4a99,0x49024887,
0x4bcc4be9,0x432840cb,0x496b49d8,0x49e34976,0x4b714ba4,0x45df44bd,0x487a48f6,0x4aa24a47,0x4aeb4b33,0x480546f9,0x46dd47ee,0x4b3a4af3,
0x4bf94c00,0x3d330000,0x49f44a5e,0x495848d8,0x4bc34be5,0x43ba412e,0x49024980,0x4a3d49d0,0x4b594b95,0x4654451d,0x47dd487c,0x4af74aa0,
0x4abd4b11,0x48504780,0x458146b5,0x4b834b43,0x4bf84c00,0x3d970000,0x49a64a1f,0x49aa4927,0x4bba4be1,0x44264191,0x48944922,0x4a904a23,
0x4b3f4b84,0x46c6457c,0x46bb47f9,0x4b424af0,0x4a8c4aed,0x48994802,0x441a4570,0x4bbc4b86,0x4bf74c00,0x3dfb0000,0x495449dc,0x49f84972,
0x4bb04bdc,0x446f41f4,0x482048bf,0x4adb4a71,0x4b244b72,0x473745da,0x458d46ee,0x4b814b36,0x4a584ac6,0x48e04842,0x41534420,0x4be34bbb,
0x4bf64c00,0x3e5f0000,0x48fd4996,0x4a4149ba,0x4ba54bd7,0x44b74257,0x474e4858,0x4b1e4ab8,0x4b074b5f,0x47a64637,0x445745da,0x4bb34b72,
0x4a214a9c,0x49244881,0x3cce4191,0x4bfa4be1,0x4bf54c00,0x3ec30000,0x48a3494d,0x4a8549fe,0x4b9a4bd2,0x44ff42b9,0x465447d8,0x4b594af9,
0x4ae84b4b,0x480a4693,0x423244bd,0x4bd94ba4,0x49e74a71,0x496648bf,0xb4523db0,0x4c004bf8,0x4bf34c00,0x3f270000,0x48454900,0x4ac44a3f,
0x4b8e4bcd,0x4546431b,0x455246f9,0x4b8b4b33,0x4ac74b36,0x484046ee,0x3f594334,0x4bf24bcb,0x49aa4a43,0x49a648fb,0xbef52a48,0x4bf44c00,
0x4bf24c00,0x3f8b0000,0x47c848b0,0x4afe4a7c,0x4b814bc7,0x458d437d,0x444b4614,0x4bb54b67,0x4aa54b20,0x48744748,0x388440e4,0x4bff4be8,
0x496b4a13,0x49e34935,0xc263bd4c,0x4bd74bf9,0x4bf04c00,0x3fef0000,0x46ff485d,0x4b324ab5,0x4b734bc1,0x45d443df,0x427c4529,0x4bd64b93,
0x4a814b08,0x48a847a1,0xb9b13d1a,0x4bfe4bf9,0x492949e1,0x4a1d496d,0xc49fc160,0x4ba94be3,0x4bef4c00,0x40290000,0x46314807,0x4b604ae9,
0x4b654bbb,0x461a4420,0x405b4438,0x4bed4bb7,0x4a5c4af0,0x48db47f9,0xbfef2e48,0x4bf04c00,0x48e549ad,0x4a5449a4,0xc602c408,0x4b6a4bbe,
0x4bed4c00,0x405b0000,0x455e475e,0x4b894b1a,0x4b574bb4,0x465f4451,0x3c6a4288,0x4bfb4bd5,0x4a354ad6,0x490c4828,0xc27cbc51,0x4bd64bfb,
0x489e4976,0x4a8949d8,0xc759c558,0x4b1b4b8a,0x4beb4c00,0x408d0000,0x448746aa,0x4bac4b46,0x4b474bad,0x46a44481,0x26484099,0x4c004beb,
0x4a0d4abc,0x493c4852,0xc47bc080,0x4bae4bec,0x4855493e,0x4aba4a0b,0xc850c69e,0x4abd4b49,0x4be94c00,0x40be0000,0x435945f1,0x4bc94b6e,
0x4b374ba6,0x46e844b1,0xbc383d4c,0x4bfc4bf9,0x49e34aa0,0x496b487c,0xc5b1c2d2,0x4b7a4bd1,0x480a4905,0x4ae84a3b,0xc8eac7d8,0x4a504af9,
0x4be74c00,0x40f00000,0x419e4534,0x4be04b91,0x4b274b9e,0x472c44e1,0xc042357f,0x4bee4c00,0x49b84a83,0x499948a6,0xc6ddc48d,0x4b3a4bab,
0x477a48c9,0x4b134a69,0xc979c881,0x49d64a9c,0x4be54c00,0x41220000,0x3fbd4475,0x4bf14baf,0x4b164b97,0x476f4511,0xc263b91b,0x4bd74bfe,
0x498b4a65,0x49c548ce,0xc7fec5ab,0x4aee4b7b,0x46dd488c,0x4b3a4a95,0xc9fcc90e,0x494f4a33,0x4be34c00,0x41530000,0x3c384365,0x4bfc4bc9,
0x4b044b8f,0x47b24540,0xc43ebe78,0x4bb74bf6,0x495d4a47,0x49f048f6,0xc889c6c1,0x4a974b41,0x463c484d,0x4b5e4abf,0xca73c992,0x48bc49be,
0x4be14c00,0x41850000,0x317f41db,0x4c004bdd,0x4af14b86,0x47f34570,0xc546c12e,0x4b8e4be5,0x492e4a27,0x4a19491d,0xc90cc7cd,0x4a354afc,
0x4599480d,0x4b7f4ae6,0xcadbca0b,0x4820493e,0x4bdf4c00,0x41b60000,0xb9b1404e,0x4bfe4bed,0x4ade4b7d,0x481a459f,0xc648c31b,0x4b5c4bcd,
0x48fd4a07,0x4a414943,0xc986c867,0x49c94aae,0x44f34796,0x4b9c4b0b,0xcb35ca78,0x46f448b5,0x4bdd4c00,0x41e80000,0xbe5f3d7e,0x4bf64bf8,
0x4acb4b74,0x483a45ce,0xc742c481,0x4b214bad,0x48cc49e5,0x4a674969,0xc9f8c8e2,0x49544a56,0x444b4710,0x4bb54b2e,0xcb7fcad9,0x45994822,
0x4bda4c00,0x42190000,0xc0f038b6,0x4be74bff,0x4ab64b6b,0x485a45fd,0xc81ac570,0x4ade4b86,0x489949c3,0x4a8c498d,0xca60c956,0x48d649f6,
0x43404687,0x4bcb4b4e,0xcbb8cb2e,0x44324710,0x4bd84c00,0x424b0000,0xc2adb248,0x4bd34c00,0x4aa24b62,0x487a462b,0xc88ec659,0x4a934b58,
0x4865499f,0x4ab049b1,0xcabdc9c3,0x4850498d,0x41e845fd,0x4bdd4b6b,0xcbe1cb74,0x418545ce,0x4bd64c00,0x427c0000,0xc432bbd9,0x4bb84bfc,
0x4a8c4b58,0x48994659,0xc8fdc73d,0x4a414b22,0x4830497b,0x4ad149d4,0xcb10ca27,0x4785491d,0x408d4570,0x4beb4b86,0xcbf9cbad,0x3d334481,
0x4bd34c00,0x42ad0000,0xc50bbf0e,0x4b984bf4,0x4a764b4e,0x48b74687,0xc966c80d,0x49e74ae6,0x47f34956,0x4af149f6,0xcb57ca83,0x465f48a6,
0x3e5f44e1,0x4bf64b9e,0xcc00cbd7,0xb17f4257,0x4bd04c00,0x42de0000,0xc5dfc115,0x4b714be6,0x4a604b43,0x48d646b5,0xc9c9c877,0x49864aa3,
0x47854930,0x4b104a17,0xcb92cad6,0x452f4828,0x3b434451,0x4bfd4bb4,0xcbf5cbf3,0xbe913f40,0x4bce4c00,0x430f0000,0xc6afc2a1,0x4b454bd4,
0x4a494b39,0x48f346e3,0xca25c8dd,0x491f4a5a,0x47154909,0x4b2c4a37,0xcbc0cb20,0x43eb4748,0x3311437d,0x4c004bc7,0xcbd9cbff,0xc2323711,
0x4bcb4c00,0x43400000,0xc77ac414,0x4b134bbc,0x4a314b2e,0x49114710,0xca7ac93e,0x48b24a0b,0x46a448e2,0x4b474a56,0xcbe2cb5f,0x416c4637,
0xb7764257,0x4bff4bd7,0xcbaccbfd,0xc487bb75,0x4bc84c00,0x43710000,0xc820c4d5,0x4adb4ba0,0x4a194b22,0x492e473d,0xcac7c99b,0x484049b5,
0x463148ba,0x4b604a74,0xcbf8cb95,0x3dc9451d,0xbc9c412e,0x4bfb4be5,0xcb6fcbeb,0xc5ebc099,0x4bc54c00,0x43a20000,0xc87fc593,0x4a9e4b80,
0x4a004b17,0x494a476a,0xcb0dc9f2,0x4790495b,0x45bc4891,0x4b784a92,0xcc00cbc0,0x317f43f7,0xbf594004,0x4bf24bf0,0xcb21cbca,0xc742c34c,
0x4bc24c00,0x43d30000,0xc8dbc64e,0x4a5c4b5a,0x49e74b0b,0x49664796,0xcb4aca43,0x469948fb,0x45464867,0x4b8e4aae,0xcbfbcbe0,0xbc6a41aa,
0xc1093db0,0x4be64bf8,0xcac4cb9b,0xc845c4f9,0x4bbf4c00,0x44020000,0xc933c705,0x4a154b30,0x49cd4aff,0x498247c2,0xcb7fca8e,0x45994896,
0x44cf483d,0x4ba14ac9,0xcbe9cbf5,0xc0be3eaa,0xc2633aac,0x4bd74bfd,0xca58cb5d,0xc8e0c642,0x4bbc4c00,0x441a0000,0xc986c7b7,0x49c94b02,
0x49b34af3,0x499d47ee,0xcbabcad3,0x4493482d,0x44574812,0x4bb34ae3,0xcbcbcbff,0xc34037da,0xc3ba33db,0x4bc34c00,0xc9dfcb11,0xc970c780,
0x4bb84c00,0x44320000,0xc9d6c832,0x49794ad0,0x49994ae6,0x49b8480d,0xcbcecb11,0x430f4780,0x43ba47cd,0x4bc34afc,0xcb9fcbfe,0xc4dbb97f,
0xc487b57f,0x4bac4c00,0xc958cab8,0xc9f4c858,0x4bb54c00,0x444b0000,0xca21c887,0x49244a99,0x497d4ad9,0x49d24822,0xcbe7cb49,0x40f0469e,
0x42c64775,0x4bd24b14,0xcb68cbf2,0xc60ebf72,0xc52fbb75,0x4b924bfd,0xc8c7ca52,0xca6bc8e7,0x4bb24c00,0x44630000,0xca67c8d8,0x48cc4a5e,
0x49624acc,0x49eb4838,0xcbf8cb79,0x3d9745b6,0x41cf471b,0x4bde4b2b,0xcb24cbdb,0xc737c20d,0xc5d4be14,0x4b734bf7,0xc82ac9e1,0xcad5c96d,
0x4bae4c00,0x447b0000,0xcaa9c927,0x486f4a1f,0x49464abf,0x4a04484d,0xcc00cba2,0x351b44c9,0x40d746c1,0x4be84b41,0xcad5cbb9,0xc82ac42c,
0xc676c036,0x4b524bee,0xc70ac964,0xcb2fc9e9,0x4bab4c00,0x44930000,0xcae5c972,0x480f49dc,0x49294ab1,0x4a1d4862,0xcbfecbc4,0xba1643ae,
0x3fbd4665,0x4bf14b55,0xca7acb8c,0xc8b2c54c,0xc715c160,0x4b2c4be3,0xc5b1c8dd,0xcb7aca5a,0x4ba74c00,0x44ab0000,0xcb1bc9ba,0x47594996,
0x490c4aa3,0x4a354877,0xcbf2cbdf,0xbf5941c3,0x3dc94608,0x4bf84b69,0xca15cb55,0xc933c665,0xc7b2c288,0x4b044bd5,0xc44bc84d,0xcbb5cabf,
0x4ba34c00,0x44c30000,0xcb4cc9fe,0x468d494d,0x48ee4a95,0x4a4d488c,0xcbdecbf1,0xc1cf3fa4,0x3ba745ab,0x4bfc4b7b,0xc9a6cb14,0xc9aac775,
0xc825c3ae,0x4ad84bc4,0xc1b6c76a,0xcbdfcb17,0x4b9f4c00,0x44db0000,0xcb78ca3f,0x45bc4900,0x48d14a87,0x4a6448a0,0xcbc0cbfd,0xc3eb3b75,
0x3776454c,0x4bff4b8c,0xc92ecac9,0xca19c83d,0xc86fc469,0x4aa94bb1,0xbd97c62b,0xcbf8cb62,0x4b9c4c00,0x44f30000,0xcb9eca7c,0x44e748b0,
0x48b24a78,0x4a7a48b5,0xcb9acc00,0xc4ffaa48,0xa64844ed,0x4c004b9d,0xc8adca74,0xca7ec8ba,0xc8b7c4f9,0x4a764b9b,0x2cb6c4e1,0xcc00cb9e,
0x4b984c00,0x450b0000,0xcbbdcab5,0x440e485d,0x48944a69,0x4a9048c9,0xcb6acbfc,0xc602bc1f,0xb81f448d,0x4bff4bab,0xc825ca17,0xcad8c930,
0xc8fdc587,0x4a414b82,0x3e2dc31b,0xcbf6cbcd,0x4b944c00,0x45230000,0xcbd7cae9,0x42634807,0x48744a5a,0x4aa548dd,0xcb32cbf0,0xc6ffc004,
0xbc06442c,0x4bfc4bb9,0xc72cc9b1,0xcb27c99f,0xc941c614,0x4a094b67,0x4201c067,0xcbdccbed,0x4b904c00,0x453a0000,0xcbeacb1a,0x40a6475e,
0x48554a4b,0x4aba48f1,0xcaf1cbdc,0xc7f3c1f4,0xbdfb4396,0x4bf74bc6,0xc602c943,0xcb6aca07,0xc982c69e,0x49cd4b49,0x446fbaac,0xcbb0cbfd,
0x4b8b4c00,0x45520000,0xcbf8cb46,0x3dc946aa,0x48354a3b,0x4ace4905,0xcaa9cbc1,0xc86fc3df,0xbfef42d2,0x4bf04bd1,0xc4cfc8ce,0xcba1ca65,
0xc9c0c726,0x49904b28,0x45d43852,0xcb73cbff,0x4b874c00,0x456a0000,0xcbffcb6e,0x388445f1,0x48154a2b,0x4ae14918,0xca58cb9e,0xc8e0c4e1,
0xc0f0420d,0x4be74bdb,0xc328c852,0xcbcccabc,0xc9fcc7ac,0x494f4b05,0x472c3fa4,0xcb27cbf1,0x4b834c00,0x45810000,0xcc00cb91,0xb51b4534,
0x47e84a1b,0x4af4492b,0xca00cb74,0xc94ac5ce,0xc1e84147,0x4bdd4be4,0xc0a6c7a1,0xcbeacb08,0xca35c817,0x490c4ae0,0x483a4288,0xcacbcbd5,
0x4b7f4c00,0x45990000,0xcbfacbaf,0xbcce4475,0x47a64a0b,0x4b07493e,0xc9a1cb43,0xc9afc6b5,0xc2de4080,0x4bd04bec,0xbc38c693,0xcbfccb4b,
0xca6bc858,0x48c74ab8,0x48d64499,0xca60cbaa,0x4b7a4c00,0x45b10000,0xcbefcbc9,0xc0294365,0x476449fa,0x4b184951,0xc93ccb0b,0xca0dc796,
0xc3d33f72,0x4bc24bf2,0x3311c57c,0xcc00cb84,0xca9ec896,0x487f4a8e,0x496645e5,0xc9e7cb70,0x4b764c00,0x45c80000,0xcbddcbdd,0xc1e841db,
0x472149e9,0x4b2a4964,0xc8d1cacc,0xca64c838,0xc4633de2,0x4bb24bf7,0x3dfbc45d,0xcbf7cbb2,0xcacec8d3,0x48354a62,0x49eb4726,0xc962cb28,
0x4b714c00,0x45df0000,0xcbc5cbed,0xc3a2404e,0x46dd49d8,0x4b3a4976,0xc85fca87,0xcab3c8a0,0xc4db3c51,0x4b9f4bfb,0x4185c26f,0xcbe1cbd6,
0xcafbc90e,0x47d24a33,0x4a64482d,0xc8d1cad3,0x4b6c4c00,0x45f70000,0xcba7cbf8,0xc4ab3d7e,0x469949c7,0x4b4a4989,0xc7d2ca3b,0xcafbc905,
0xc552397f,0x4b8b4bfe,0x4402c01d,0xcbbfcbef,0xcb24c948,0x47374a02,0x4ace48bf,0xc835ca71,0x4b684c00,0x460e0000,0xcb83cbff,0xc58138b6,
0x465449b5,0x4b59499b,0xc6ddc9e9,0xcb3ac964,0xc5c834b6,0x4b764c00,0x453abb11,0xcb90cbfd,0xcb4ac980,0x469949d0,0x4b2a4948,0xc721ca02,
0x2c002c00,0x2c002c00,0x2c002c00,0x2c002c00,0x2b642c00,0x261f29a8,0xa61f0000,0xab64a9a8,0x29a82c00,0xa9a80000,0xa9a8ac00,0x29a80000,
0x261f2c00,0xab64a9a8,0x2b640000,0xa61f29a8,0x2c00,0xac00,0x2c00,0xac00,0xa61f2c00,0x2b64a9a8,0xab640000,0x261f29a8,
0xa9a82c00,0x29a80000,0x29a8ac00,0xa9a80000,0xab642c00,0xa61f29a8,0x261f0000,0x2b64a9a8,0,0,0,0,
0x261f0000,0x2b6429a8,0x2b642c00,0x261f29a8,0x29a80000,0x29a82c00,0xa9a80000,0xa9a8ac00,0x2b640000,0xa61f29a8,0xa61fac00,0x2b6429a8,
0x2c000000,0xac000000,0x2c000000,0xac000000,0x2b640000,0xa61fa9a8,0xa61f2c00,0x2b64a9a8,0x29a80000,0x29a8ac00,0xa9a80000,0xa9a82c00,
0x261f0000,0x2b64a9a8,0x2b64ac00,0x261fa9a8,0xac002c00,0xac002c00,0xac002c00,0xac002c00,0xab642c00,0xa61f29a8,0x261f0000,0x2b64a9a8,
0xa9a82c00,0x29a80000,0x29a8ac00,0xa9a80000,0xa61f2c00,0x2b64a9a8,0xab640000,0x261f29a8,0x2c00,0xac00,0x2c00,0xac00,
0x261f2c00,0xab64a9a8,0x2b640000,0xa61f29a8,0x29a82c00,0xa9a80000,0xa9a8ac00,0x29a80000,0x2b642c00,0x261f29a8,0xa61f0000,0xab64a9a8,
0,0,0,0,0xa61f0000,0xab6429a8,0xab642c00,0xa61f29a8,0xa9a80000,0xa9a82c00,0x29a80000,0x29a8ac00,
0xab640000,0x261f29a8,0x261fac00,0xab6429a8,0xac000000,0x2c000000,0xac000000,0x2c000000,0xab640000,0x261fa9a8,0x261f2c00,0xab64a9a8,
0xa9a80000,0xa9a8ac00,0x29a80000,0x29a82c00,0xa61f0000,0xab64a9a8,0xab64ac00,0xa61fa9a8,0,0,0,0,
0xa61f0000,0xab64a9a8,0xab64ac00,0xa61fa9a8,0xa9a80000,0xa9a8ac00,0x29a80000,0x29a82c00,0xab640000,0x261fa9a8,0x261f2c00,0xab64a9a8,
0xac000000,0x2c000000,0xac000000,0x2c000000,0xab640000,0x261f29a8,0x261fac00,0xab6429a8,0xa9a80000,0xa9a82c00,0x29a80000,0x29a8ac00,
0xa61f0000,0xab6429a8,0xab642c00,0xa61f29a8,0x2c002c00,0x2c002c00,0x2c002c00,0x2c002c00,0x2b642c00,0x261f29a8,0xa61f0000,0xab64a9a8,
0x29a82c00,0xa9a80000,0xa9a8ac00,0x29a80000,0x261f2c00,0xab64a9a8,0x2b640000,0xa61f29a8,0x2c00,0xac00,0x2c00,0xac00,
0xa61f2c00,0x2b64a9a8,0xab640000,0x261f29a8,0xa9a82c00,0x29a80000,0x29a8ac00,0xa9a80000,0xab642c00,0xa61f29a8,0x261f0000,0x2b64a9a8,
0,0,0,0,0x261f0000,0x2b64a9a8,0x2b64ac00,0x261fa9a8,0x29a80000,0x29a8ac00,0xa9a80000,0xa9a82c00,
0x2b640000,0xa61fa9a8,0xa61f2c00,0x2b64a9a8,0x2c000000,0xac000000,0x2c000000,0xac000000,0x2b640000,0xa61f29a8,0xa61fac00,0x2b6429a8,
0x29a80000,0x29a82c00,0xa9a80000,0xa9a8ac00,0x261f0000,0x2b6429a8,0x2b642c00,0x261f29a8,0xac002c00,0xac002c00,0xac002c00,0xac002c00,
0xab642c00,0xa61f29a8,0x261f0000,0x2b64a9a8,0xa9a82c00,0x29a80000,0x29a8ac00,0xa9a80000,0xa61f2c00,0x2b64a9a8,0xab640000,0x261f29a8,
0x2c00,0xac00,0x2c00,0xac00,0x261f2c00,0xab64a9a8,0x2b640000,0xa61f29a8,0x29a82c00,0xa9a80000,0xa9a8ac00,0x29a80000,
0x2b642c00,0x261f29a8,0xa61f0000,0xab64a9a8,0x2c002c00,0x2c002c00,0x2c002c00,0x2c002c00,0xab64ac00,0xa61fa9a8,0x261f0000,0x2b6429a8,
0x29a82c00,0xa9a80000,0xa9a8ac00,0x29a80000,0xa61fac00,0x2b6429a8,0xab640000,0x261fa9a8,0x2c00,0xac00,0x2c00,0xac00,
0x261fac00,0xab6429a8,0x2b640000,0xa61fa9a8,0xa9a82c00,0x29a80000,0x29a8ac00,0xa9a80000,0x2b64ac00,0x261fa9a8,0xa61f0000,0xab6429a8,
0,0,0,0,0xa61f0000,0xab64a9a8,0xab64ac00,0xa61fa9a8,0x29a80000,0x29a82c00,0xa9a80000,0xa9a8ac00,
0xab640000,0x261fa9a8,0x261f2c00,0xab64a9a8,0x2c000000,0xac000000,0x2c000000,0xac000000,0xab640000,0x261f29a8,0x261fac00,0xab6429a8,
0x29a80000,0x29a8ac00,0xa9a80000,0xa9a82c00,0xa61f0000,0xab6429a8,0xab642c00,0xa61f29a8,0xac002c00,0xac002c00,0xac002c00,0xac002c00,
0x2b64ac00,0x261fa9a8,0xa61f0000,0xab6429a8,0xa9a82c00,0x29a80000,0x29a8ac00,0xa9a80000,0x261fac00,0xab6429a8,0x2b640000,0xa61fa9a8,
0x2c00,0xac00,0x2c00,0xac00,0xa61fac00,0x2b6429a8,0xab640000,0x261fa9a8,0x29a82c00,0xa9a80000,0xa9a8ac00,0x29a80000,
0xab64ac00,0xa61fa9a8,0x261f0000,0x2b6429a8,0,0,0,0,0x261f0000,0x2b64a9a8,0x2b64ac00,0x261fa9a8,
0xa9a80000,0xa9a82c00,0x29a80000,0x29a8ac00,0x2b640000,0xa61fa9a8,0xa61f2c00,0x2b64a9a8,0xac000000,0x2c000000,0xac000000,0x2c000000,
0x2b640000,0xa61f29a8,0xa61fac00,0x2b6429a8,0xa9a80000,0xa9a8ac00,0x29a80000,0x29a82c00,0x261f0000,0x2b6429a8,0x2b642c00,0x261f29a8,
0,0,0,0,0x261f0000,0x2b6429a8,0x2b642c00,0x261f29a8,0xa9a80000,0xa9a8ac00,0x29a80000,0x29a82c00,
0x2b640000,0xa61f29a8,0xa61fac00,0x2b6429a8,0xac000000,0x2c000000,0xac000000,0x2c000000,0x2b640000,0xa61fa9a8,0xa61f2c00,0x2b64a9a8,
0xa9a80000,0xa9a82c00,0x29a80000,0x29a8ac00,0x261f0000,0x2b64a9a8,0x2b64ac00,0x261fa9a8,0x2c002c00,0x2c002c00,0x2c002c00,0x2c002c00,
0xab64ac00,0xa61fa9a8,0x261f0000,0x2b6429a8,0x29a82c00,0xa9a80000,0xa9a8ac00,0x29a80000,0xa61fac00,0x2b6429a8,0xab640000,0x261fa9a8,
0x2c00,0xac00,0x2c00,0xac00,0x261fac00,0xab6429a8,0x2b640000,0xa61fa9a8,0xa9a82c00,0x29a80000,0x29a8ac00,0xa9a80000,
0x2b64ac00,0x261fa9a8,0xa61f0000,0xab6429a8,0,0,0,0,0xa61f0000,0xab6429a8,0xab642c00,0xa61f29a8,
0x29a80000,0x29a8ac00,0xa9a80000,0xa9a82c00,0xab640000,0x261f29a8,0x261fac00,0xab6429a8,0x2c000000,0xac000000,0x2c000000,0xac000000,
0xab640000,0x261fa9a8,0x261f2c00,0xab64a9a8,0x29a80000,0x29a82c00,0xa9a80000,0xa9a8ac00,0xa61f0000,0xab64a9a8,0xab64ac00,0xa61fa9a8,
0xac002c00,0xac002c00,0xac002c00,0xac002c00,0x2b64ac00,0x261fa9a8,0xa61f0000,0xab6429a8,0xa9a82c00,0x29a80000,0x29a8ac00,0xa9a80000,
0x261fac00,0xab6429a8,0x2b640000,0xa61fa9a8,0x2c00,0xac00,0x2c00,0xac00,0xa61fac00,0x2b6429a8,0xab640000,0x261fa9a8,
0x29a82c00,0xa9a80000,0xa9a8ac00,0x29a80000,0xab64ac00,0xa61fa9a8,0x261f0000,0x2b6429a8,0x2bd92c00,0x2aa72b64,0x287229a8,0x223e261f,
0x2aa72c00,0xa23e261f,0xabd9a9a8,0xa872ab64,0x28722c00,0xabd9a61f,0x223ea9a8,0x2aa72b64,0x223e2c00,0xa872ab64,0x2aa729a8,0xabd9a61f,
0xa23e2c00,0x2872ab64,0xaaa729a8,0x2bd9a61f,0xa8722c00,0x2bd9a61f,0xa23ea9a8,0xaaa72b64,0xaaa72c00,0x223e261f,0x2bd9a9a8,0x2872ab64,
0xabd92c00,0xaaa72b64,0xa87229a8,0xa23e261f,0x223e0000,0x2872261f,0x2aa729a8,0x2bd92b64,0x28720000,0x2bd92b64,0x223e29a8,0xaaa7a61f,
0x2aa70000,0x223e2b64,0xabd9a9a8,0x2872a61f,0x2bd90000,0xaaa7261f,0x2872a9a8,0xa23e2b64,0x2bd90000,0xaaa7a61f,0x287229a8,0xa23eab64,
0x2aa70000,0x223eab64,0xabd929a8,0x2872261f,0x28720000,0x2bd9ab64,0x223ea9a8,0xaaa7261f,0x223e0000,0x2872a61f,0x2aa7a9a8,0x2bd9ab64,
0xabd92c00,0xaaa72b64,0xa87229a8,0xa23e261f,0xaaa72c00,0x223e261f,0x2bd9a9a8,0x2872ab64,0xa8722c00,0x2bd9a61f,0xa23ea9a8,0xaaa72b64,
0xa23e2c00,0x2872ab64,0xaaa729a8,0x2bd9a61f,0x223e2c00,0xa872ab64,0x2aa729a8,0xabd9a61f,0x28722c00,0xabd9a61f,0x223ea9a8,0x2aa72b64,
0x2aa72c00,0xa23e261f,0xabd9a9a8,0xa872ab64,0x2bd92c00,0x2aa72b64,0x287229a8,0x223e261f,0xa23e0000,0xa872261f,0xaaa729a8,0xabd92b64,
0xa8720000,0xabd92b64,0xa23e29a8,0x2aa7a61f,0xaaa70000,0xa23e2b64,0x2bd9a9a8,0xa872a61f,0xabd90000,0x2aa7261f,0xa872a9a8,0x223e2b64,
0xabd90000,0x2aa7a61f,0xa87229a8,0x223eab64,0xaaa70000,0xa23eab64,0x2bd929a8,0xa872261f,0xa8720000,0xabd9ab64,0xa23ea9a8,0x2aa7261f,
0xa23e0000,0xa872a61f,0xaaa7a9a8,0xabd9ab64,0xa23e0000,0xa872a61f,0xaaa7a9a8,0xabd9ab64,0xa8720000,0xabd9ab64,0xa23ea9a8,0x2aa7261f,
0xaaa70000,0xa23eab64,0x2bd929a8,0xa872261f,0xabd90000,0x2aa7a61f,0xa87229a8,0x223eab64,0xabd90000,0x2aa7261f,0xa872a9a8,0x223e2b64,
0xaaa70000,0xa23e2b64,0x2bd9a9a8,0xa872a61f,0xa8720000,0xabd92b64,0xa23e29a8,0x2aa7a61f,0xa23e0000,0xa872261f,0xaaa729a8,0xabd92b64,
0x2bd92c00,0x2aa72b64,0x287229a8,0x223e261f,0x2aa72c00,0xa23e261f,0xabd9a9a8,0xa872ab64,0x28722c00,0xabd9a61f,0x223ea9a8,0x2aa72b64,
0x223e2c00,0xa872ab64,0x2aa729a8,0xabd9a61f,0xa23e2c00,0x2872ab64,0xaaa729a8,0x2bd9a61f,0xa8722c00,0x2bd9a61f,0xa23ea9a8,0xaaa72b64,
0xaaa72c00,0x223e261f,0x2bd9a9a8,0x2872ab64,0xabd92c00,0xaaa72b64,0xa87229a8,0xa23e261f,0x223e0000,0x2872a61f,0x2aa7a9a8,0x2bd9ab64,
0x28720000,0x2bd9ab64,0x223ea9a8,0xaaa7261f,0x2aa70000,0x223eab64,0xabd929a8,0x2872261f,0x2bd90000,0xaaa7a61f,0x287229a8,0xa23eab64,
0x2bd90000,0xaaa7261f,0x2872a9a8,0xa23e2b64,0x2aa70000,0x223e2b64,0xabd9a9a8,0x2872a61f,0x28720000,0x2bd92b64,0x223e29a8,0xaaa7a61f,
0x223e0000,0x2872261f,0x2aa729a8,0x2bd92b64,0xabd92c00,0xaaa72b64,0xa87229a8,0xa23e261f,0xaaa72c00,0x223e261f,0x2bd9a9a8,0x2872ab64,
0xa8722c00,0x2bd9a61f,0xa23ea9a8,0xaaa72b64,0xa23e2c00,0x2872ab64,0xaaa729a8,0x2bd9a61f,0x223e2c00,0xa872ab64,0x2aa729a8,0xabd9a61f,
0x28722c00,0xabd9a61f,0x223ea9a8,0x2aa72b64,0x2aa72c00,0xa23e261f,0xabd9a9a8,0xa872ab64,0x2bd92c00,0x2aa72b64,0x287229a8,0x223e261f,
0xa23e0000,0xa872a61f,0xaaa7a9a8,0xabd9ab64,0x28720000,0x2bd92b64,0x223e29a8,0xaaa7a61f,0xaaa70000,0xa23eab64,0x2bd929a8,0xa872261f,
0x2bd90000,0xaaa7261f,0x2872a9a8,0xa23e2b64,0xabd90000,0x2aa7261f,0xa872a9a8,0x223e2b64,0x2aa70000,0x223eab64,0xabd929a8,0x2872261f,
0xa8720000,0xabd92b64,0xa23e29a8,0x2aa7a61f,0x223e0000,0x2872a61f,0x2aa7a9a8,0x2bd9ab64,0x2bd92c00,0x2aa72b64,0x287229a8,0x223e261f,
0xaaa7ac00,0x223ea61f,0x2bd929a8,0x28722b64,0x28722c00,0xabd9a61f,0x223ea9a8,0x2aa72b64,0xa23eac00,0x28722b64,0xaaa7a9a8,0x2bd9261f,
0xa23e2c00,0x2872ab64,0xaaa729a8,0x2bd9a61f,0x2872ac00,0xabd9261f,0x223e29a8,0x2aa7ab64,0xaaa72c00,0x223e261f,0x2bd9a9a8,0x2872ab64,
0x2bd9ac00,0x2aa7ab64,0x2872a9a8,0x223ea61f,0x223e0000,0x2872a61f,0x2aa7a9a8,0x2bd9ab64,0xa8720000,0xabd92b64,0xa23e29a8,0x2aa7a61f,
0x2aa70000,0x223eab64,0xabd929a8,0x2872261f,0xabd90000,0x2aa7261f,0xa872a9a8,0x223e2b64,0x2bd90000,0xaaa7261f,0x2872a9a8,0xa23e2b64,
0xaaa70000,0xa23eab64,0x2bd929a8,0xa872261f,0x28720000,0x2bd92b64,0x223e29a8,0xaaa7a61f,0xa23e0000,0xa872a61f,0xaaa7a9a8,0xabd9ab64,
0xabd92c00,0xaaa72b64,0xa87229a8,0xa23e261f,0x2aa7ac00,0xa23ea61f,0xabd929a8,0xa8722b64,0xa8722c00,0x2bd9a61f,0xa23ea9a8,0xaaa72b64,
0x223eac00,0xa8722b64,0x2aa7a9a8,0xabd9261f,0x223e2c00,0xa872ab64,0x2aa729a8,0xabd9a61f,0xa872ac00,0x2bd9261f,0xa23e29a8,0xaaa7ab64,
0x2aa72c00,0xa23e261f,0xabd9a9a8,0xa872ab64,0xabd9ac00,0xaaa7ab64,0xa872a9a8,0xa23ea61f,0xabd9ac00,0xaaa7ab64,0xa872a9a8,0xa23ea61f,
0x2aa72c00,0xa23e261f,0xabd9a9a8,0xa872ab64,0xa872ac00,0x2bd9261f,0xa23e29a8,0xaaa7ab64,0x223e2c00,0xa872ab64,0x2aa729a8,0xabd9a61f,
0x223eac00,0xa8722b64,0x2aa7a9a8,0xabd9261f,0xa8722c00,0x2bd9a61f,0xa23ea9a8,0xaaa72b64,0x2aa7ac00,0xa23ea61f,0xabd929a8,0xa8722b64,
0xabd92c00,0xaaa72b64,0xa87229a8,0xa23e261f,0xa23e0000,0xa872a61f,0xaaa7a9a8,0xabd9ab64,0x28720000,0x2bd92b64,0x223e29a8,0xaaa7a61f,
0xaaa70000,0xa23eab64,0x2bd929a8,0xa872261f,0x2bd90000,0xaaa7261f,0x2872a9a8,0xa23e2b64,0xabd90000,0x2aa7261f,0xa872a9a8,0x223e2b64,
0x2aa70000,0x223eab64,0xabd929a8,0x2872261f,0xa8720000,0xabd92b64,0xa23e29a8,0x2aa7a61f,0x223e0000,0x2872a61f,0x2aa7a9a8,0x2bd9ab64,
0x2bd9ac00,0x2aa7ab64,0x2872a9a8,0x223ea61f,0xaaa72c00,0x223e261f,0x2bd9a9a8,0x2872ab64,0x2872ac00,0xabd9261f,0x223e29a8,0x2aa7ab64,
0xa23e2c00,0x2872ab64,0xaaa729a8,0x2bd9a61f,0xa23eac00,0x28722b64,0xaaa7a9a8,0x2bd9261f,0x28722c00,0xabd9a61f,0x223ea9a8,0x2aa72b64,
0xaaa7ac00,0x223ea61f,0x2bd929a8,0x28722b64,0x2bd92c00,0x2aa72b64,0x287229a8,0x223e261f,0x223e0000,0x2872a61f,0x2aa7a9a8,0x2bd9ab64,
0xa8720000,0xabd92b64,0xa23e29a8,0x2aa7a61f,0x2aa70000,0x223eab64,0xabd929a8,0x2872261f,0xabd90000,0x2aa7261f,0xa872a9a8,0x223e2b64,
0x2bd90000,0xaaa7261f,0x2872a9a8,0xa23e2b64,0xaaa70000,0xa23eab64,0x2bd929a8,0xa872261f,0x28720000,0x2bd92b64,0x223e29a8,0xaaa7a61f,
0xa23e0000,0xa872a61f,0xaaa7a9a8,0xabd9ab64,0x27fe2800,0x96480000,0x273b2764,0xa2d7a21f,0x27ea27f6,0x9cb29a46,0x26dd270e,0xa41da38b,
0x27c327d9,0x9fc69e3e,0x266d26a7,0xa4c4a472,0x278827a8,0xa164a0a5,0x25ed262f,0xa55fa513,0x27c32800,0x9fc60000,0xa4c4a21f,0xa66da764,
0x25ed270e,0xa55fa38b,0xa73ba62f,0xa2d7a513,0x21642472,0xa788a6a7,0xa7fea7d9,0x16489e3e,0x9cb21a46,0xa7eaa7f6,0xa6dda7a8,0x241d20a5,
0x273b2800,0xa2d70000,0xa55fa764,0x25ed221f,0x1fc62513,0xa7c3a62f,0x1cb2a0a5,0x27ea27a8,0xa4c49e3e,0xa66da7d9,0x26dd2472,0x241d26a7,
0xa7fea70e,0x9648a38b,0x278827f6,0xa1641a46,0x266d2800,0xa4c40000,0x26dd221f,0x241d2764,0xa16420a5,0xa788a7a8,0x25ed27f6,0xa55f9a46,
0xa7fea6a7,0x1648a472,0xa2d71e3e,0xa73ba7d9,0x9fc6a62f,0x27c32513,0xa7eaa70e,0x1cb2a38b,0x255f2800,0xa5ed0000,0x21642764,0xa788a21f,
0xa66d9a46,0xa4c4a7f6,0xa7c3a38b,0x9fc6a70e,0xa41da7d9,0x26dd1e3e,0x9cb2a6a7,0x27ea2472,0x273b20a5,0x22d727a8,0x27fe2513,0x1648262f,
0x241d2800,0xa6dd0000,0xa7eaa21f,0x9cb2a764,0xa7fea38b,0x9648a70e,0x2164a513,0x2788262f,0x22d7a472,0x273b26a7,0x255f27d9,0xa5ed1e3e,
0x24c427f6,0xa66d1a46,0xa7c3a0a5,0x9fc6a7a8,0x21642800,0xa7880000,0x1648a764,0x27fe221f,0xa6dda62f,0x241da513,0x24c427a8,0xa66d20a5,
0x27ea1e3e,0x1cb227d9,0xa7c3a472,0x1fc6a6a7,0xa55f238b,0xa5eda70e,0x273b9a46,0x22d727f6,0x1cb22800,0xa7ea0000,0x27c3221f,0x9fc62764,
0xa2d7a7a8,0x273ba0a5,0xa7fe9a46,0x9648a7f6,0x255f26a7,0xa5ed2472,0x27889e3e,0x216427d9,0xa6dda513,0x241da62f,0xa66d238b,0xa4c4a70e,
0x96482800,0xa7fe0000,0xa2d72764,0xa73ba21f,0x1cb2a7f6,0x27ea1a46,0x241da70e,0x26dd238b,0x9fc627d9,0xa7c39e3e,0xa4c426a7,0xa66da472,
0x2164a7a8,0x278820a5,0x255fa62f,0x25ed2513,0x9fc62800,0xa7c30000,0xa66da21f,0x24c4a764,0x255fa70e,0x25ed238b,0x22d7262f,0xa73b2513,
0xa7882472,0xa164a6a7,0x1648a7d9,0x27fe9e3e,0x27ea9a46,0x9cb227f6,0xa41d27a8,0xa6dda0a5,0xa2d72800,0xa73b0000,0x25eda764,0x255f221f,
0x27c3a513,0x1fc6262f,0xa7ea20a5,0x1cb2a7a8,0xa66d9e3e,0x24c4a7d9,0x241d2472,0xa6dd26a7,0x1648270e,0xa7fe238b,0x2164a7f6,0x27889a46,
0xa4c42800,0xa66d0000,0x241d221f,0xa6dd2764,0x2788a0a5,0xa16427a8,0x255fa7f6,0x25ed1a46,0x1648a6a7,0x27fea472,0xa73b1e3e,0x22d7a7d9,
0xa7c3262f,0x9fc6a513,0x9cb2270e,0xa7ea238b,0xa5ed2800,0xa55f0000,0xa7882764,0xa164a21f,0x24c41a46,0xa66d27f6,0x1fc6238b,0xa7c3270e,
0x26dda7d9,0x241d1e3e,0x27eaa6a7,0x1cb22472,0xa2d7a0a5,0x273ba7a8,0x9648a513,0x27fea62f,0xa6dd2800,0xa41d0000,0x9cb2a21f,0x27eaa764,
0x1648238b,0xa7fe270e,0xa7882513,0x2164a62f,0x273ba472,0xa2d726a7,0xa5ed27d9,0xa55f1e3e,0x266da7f6,0x24c49a46,0x1fc620a5,0xa7c327a8,
0xa7882800,0xa1640000,0x27fea764,0x9648221f,0xa41d262f,0xa6dd2513,0x266da7a8,0x24c4a0a5,0x1cb21e3e,0xa7ea27d9,0x1fc6a472,0x27c3a6a7,
0x25eda38b,0xa55f270e,0xa2d71a46,0x273ba7f6,0xa7ea2800,0x9cb20000,0x9fc6221f,0xa7c32764,0xa73b27a8,0xa2d720a5,0x16481a46,0xa7fe27f6,
0xa5ed26a7,0xa55f2472,0x21649e3e,0xa78827d9,0xa41d2513,0xa6dd262f,0x24c4a38b,0xa66d270e,0xa7fe2800,0x16480000,0xa73b2764,0x22d7a21f,
0xa7ea27f6,0x1cb29a46,0xa6dd270e,0x241da38b,0xa7c327d9,0x1fc69e3e,0xa66d26a7,0x24c4a472,0xa78827a8,0x2164a0a5,0xa5ed262f,0x255fa513,
0xa7c32800,0x1fc60000,0x24c4a21f,0x266da764,0xa5ed270e,0x255fa38b,0x273ba62f,0x22d7a513,0xa1642472,0x2788a6a7,0x27fea7d9,0x96489e3e,
0x1cb21a46,0x27eaa7f6,0x26dda7a8,0xa41d20a5,0xa73b2800,0x22d70000,0x255fa764,0xa5ed221f,0x9fc62513,0x27c3a62f,0x9cb2a0a5,0xa7ea27a8,
0x24c49e3e,0x266da7d9,0xa6dd2472,0xa41d26a7,0x27fea70e,0x1648a38b,0xa78827f6,0x21641a46,0xa66d2800,0x24c40000,0xa6dd221f,0xa41d2764,
0x216420a5,0x2788a7a8,0xa5ed27f6,0x255f9a46,0x27fea6a7,0x9648a472,0x22d71e3e,0x273ba7d9,0x1fc6a62f,0xa7c32513,0x27eaa70e,0x9cb2a38b,
0xa55f2800,0x25ed0000,0xa1642764,0x2788a21f,0x266d9a46,0x24c4a7f6,0x27c3a38b,0x1fc6a70e,0x241da7d9,0xa6dd1e3e,0x1cb2a6a7,0xa7ea2472,
0xa73b20a5,0xa2d727a8,0xa7fe2513,0x9648262f,0xa41d2800,0x26dd0000,0x27eaa21f,0x1cb2a764,0x27fea38b,0x1648a70e,0xa164a513,0xa788262f,
0xa2d7a472,0xa73b26a7,0xa55f27d9,0x25ed1e3e,0xa4c427f6,0x266d1a46,0x27c3a0a5,0x1fc6a7a8,0xa1642800,0x27880000,0x9648a764,0xa7fe221f,
0x26dda62f,0xa41da513,0xa4c427a8,0x266d20a5,0xa7ea1e3e,0x9cb227d9,0x27c3a472,0x9fc6a6a7,0x255f238b,0x25eda70e,0xa73b9a46,0xa2d727f6,
0x9cb22800,0x27ea0000,0xa7c3221f,0x1fc62764,0x22d7a7a8,0xa73ba0a5,0x27fe9a46,0x1648a7f6,0xa55f26a7,0x25ed2472,0xa7889e3e,0xa16427d9,
0x26dda513,0xa41da62f,0x266d238b,0x24c4a70e,0x16482800,0x27fe0000,0x22d72764,0x273ba21f,0x9cb2a7f6,0xa7ea1a46,0xa41da70e,0xa6dd238b,
0x1fc627d9,0x27c39e3e,0x24c426a7,0x266da472,0xa164a7a8,0xa78820a5,0xa55fa62f,0xa5ed2513,0x1fc62800,0x27c30000,0x266da21f,0xa4c4a764,
0xa55fa70e,0xa5ed238b,0xa2d7262f,0x273b2513,0x27882472,0x2164a6a7,0x9648a7d9,0xa7fe9e3e,0xa7ea9a46,0x1cb227f6,0x241d27a8,0x26dda0a5,
0x22d72800,0x273b0000,0xa5eda764,0xa55f221f,0xa7c3a513,0x9fc6262f,0x27ea20a5,0x9cb2a7a8,0x266d9e3e,0xa4c4a7d9,0xa41d2472,0x26dd26a7,
0x9648270e,0x27fe238b,0xa164a7f6,0xa7889a46,0x24c42800,0x266d0000,0xa41d221f,0x26dd2764,0xa788a0a5,0x216427a8,0xa55fa7f6,0xa5ed1a46,
0x9648a6a7,0xa7fea472,0x273b1e3e,0xa2d7a7d9,0x27c3262f,0x1fc6a513,0x1cb2270e,0x27ea238b,0x25ed2800,0x255f0000,0x27882764,0x2164a21f,
0xa4c41a46,0x266d27f6,0x9fc6238b,0x27c3270e,0xa6dda7d9,0xa41d1e3e,0xa7eaa6a7,0x9cb22472,0x22d7a0a5,0xa73ba7a8,0x1648a513,0xa7fea62f,
0x26dd2800,0x241d0000,0x1cb2a21f,0xa7eaa764,0x9648238b,0x27fe270e,0x27882513,0xa164a62f,0xa73ba472,0x22d726a7,0x25ed27d9,0x255f1e3e,
0xa66da7f6,0xa4c49a46,0x9fc620a5,0x27c327a8,0x27882800,0x21640000,0xa7fea764,0x1648221f,0x241d262f,0x26dd2513,0xa66da7a8,0xa4c4a0a5,
0x9cb21e3e,0x27ea27d9,0x9fc6a472,0xa7c3a6a7,0xa5eda38b,0x255f270e,0x22d71a46,0xa73ba7f6,0x27ea2800,0x1cb20000,0x1fc6221f,0x27c32764,
0x273b27a8,0x22d720a5,0x96481a46,0x27fe27f6,0x25ed26a7,0x255f2472,0xa1649e3e,0x278827d9,0x241d2513,0x26dd262f,0xa4c4a38b,0x266d270e,
0x255f25a8,0xa5eda5a8,0x2164221f,0xa788a764,0x24c42513,0xa66da62f,0x1fc620a5,0xa7c3a7a8,0x241d2472,0xa6dda6a7,0x1cb21e3e,0xa7eaa7d9,
0x22d7238b,0xa73ba70e,0x16481a46,0xa7fea7f6,0xa41da5a8,0x26dd25a8,0x27ea2764,0x1cb2221f,0x9648a0a5,0x27fe27a8,0x278827f6,0xa1649a46,
0x22d71e3e,0x273b27d9,0x255f26a7,0xa5eda472,0x266d2513,0x24c4262f,0x1fc6238b,0xa7c3a70e,0x216425a8,0xa788a5a8,0x1648a21f,0x27fe2764,
0xa41d9a46,0xa6dda7f6,0x266d238b,0x24c4270e,0xa7eaa6a7,0x9cb2a472,0x27c327d9,0x9fc61e3e,0xa5eda7a8,0x255f20a5,0x22d7262f,0xa73ba513,
0x9cb2a5a8,0x27ea25a8,0xa7c3a764,0x1fc6a21f,0x273b238b,0x22d7270e,0x9648a513,0x27fe262f,0x255f27d9,0xa5ed9e3e,0x27882472,0x216426a7,
0xa41d1a46,0xa6dda7f6,0x24c427a8,0xa66da0a5,0x964825a8,0xa7fea5a8,0xa2d7221f,0xa73ba764,0xa7eaa62f,0x1cb2a513,0xa6dda7a8,0x241da0a5,
0x1fc6a472,0x27c326a7,0x24c49e3e,0x266d27d9,0x2788270e,0xa164238b,0x25ed27f6,0xa55f1a46,0x1fc6a5a8,0x27c325a8,0x266d2764,0xa4c4221f,
0x25ed27a8,0xa55f20a5,0xa73b9a46,0xa2d7a7f6,0xa7889e3e,0xa164a7d9,0x1648a6a7,0x27fe2472,0x1cb2a62f,0x27ea2513,0x26dd270e,0xa41d238b,
0xa2d725a8,0xa73ba5a8,0x25eda21f,0x255f2764,0x9fc6a7f6,0x27c31a46,0x9cb2270e,0xa7eaa38b,0x266d26a7,0xa4c42472,0xa41da7d9,0x26dd9e3e,
0xa7fea0a5,0x9648a7a8,0x27882513,0xa164262f,0x24c4a5a8,0x266d25a8,0xa41da764,0x26dda21f,0xa164270e,0xa788a38b,0x25ed262f,0xa55f2513,
0x1648a7d9,0x27fe1e3e,0xa73ba472,0x22d7a6a7,0x1fc627f6,0xa7c31a46,0x27ea20a5,0x9cb227a8,0xa5ed25a8,0xa55fa5a8,0xa788221f,0xa164a764,
0x266da513,0x24c4262f,0x27c3a0a5,0x1fc627a8,0xa6dd2472,0xa41da6a7,0xa7ea1e3e,0x9cb2a7d9,0x273ba38b,0x22d7270e,0x27fe9a46,0x164827f6,
0x26dda5a8,0x241d25a8,0x1cb22764,0xa7ea221f,0xa7fe20a5,0x9648a7a8,0x2164a7f6,0x27881a46,0x273b1e3e,0xa2d727d9,0xa5ed26a7,0xa55fa472,
0xa4c4a513,0x266da62f,0x27c3a38b,0x1fc6270e,0xa78825a8,0xa164a5a8,0x27fea21f,0x96482764,0x26dd1a46,0xa41d27f6,0xa4c4a38b,0x266da70e,
0x9cb2a6a7,0x27eaa472,0x9fc627d9,0xa7c31e3e,0xa55f27a8,0xa5eda0a5,0x273ba62f,0x22d72513,0x27eaa5a8,0x1cb225a8,0x1fc6a764,0x27c3a21f,
0xa2d7a38b,0x273ba70e,0xa7fe2513,0x9648a62f,0xa5ed27d9,0xa55f9e3e,0x21642472,0xa78826a7,0x26dd9a46,0xa41d27f6,0x266da7a8,0x24c420a5,
0xa7fe25a8,0x1648a5a8,0xa73b221f,0x22d7a764,0x9cb2262f,0xa7ea2513,0xa41d27a8,0xa6dd20a5,0x27c3a472,0x9fc626a7,0x266d9e3e,0xa4c427d9,
0x2164a70e,0x2788a38b,0x255fa7f6,0x25ed9a46,0x27c3a5a8,0x9fc625a8,0xa4c42764,0xa66d221f,0x255fa7a8,0x25eda0a5,0x22d71a46,0xa73b27f6,
0xa1649e3e,0x2788a7d9,0x27fea6a7,0x96482472,0xa7ea262f,0x1cb2a513,0x241da70e,0x26dda38b,0xa73b25a8,0x22d7a5a8,0x255fa21f,0xa5ed2764,
0xa7c327f6,0x9fc69a46,0x27eaa70e,0x9cb2238b,0xa4c426a7,0xa66d2472,0x26dda7d9,0x241d9e3e,0x164820a5,0xa7fe27a8,0x2164a513,0x2788a62f,
0x266da5a8,0xa4c425a8,0x26dda764,0x241da21f,0x2788a70e,0xa164238b,0x255fa62f,0x25eda513,0x27fea7d9,0x96481e3e,0x22d7a472,0x273ba6a7,
0x27c3a7f6,0x1fc69a46,0x1cb2a0a5,0x27eaa7a8,0xa55f25a8,0x25eda5a8,0xa164221f,0x2788a764,0xa4c42513,0x266da62f,0x9fc620a5,0x27c3a7a8,
0xa41d2472,0x26dda6a7,0x9cb21e3e,0x27eaa7d9,0xa2d7238b,0x273ba70e,0x96481a46,0x27fea7f6,0x241da5a8,0xa6dd25a8,0xa7ea2764,0x9cb2221f,
0x1648a0a5,0xa7fe27a8,0xa78827f6,0x21649a46,0xa2d71e3e,0xa73b27d9,0xa55f26a7,0x25eda472,0xa66d2513,0xa4c4262f,0x9fc6238b,0x27c3a70e,
0xa16425a8,0x2788a5a8,0x9648a21f,0xa7fe2764,0x241d9a46,0x26dda7f6,0xa66d238b,0xa4c4270e,0x27eaa6a7,0x1cb2a472,0xa7c327d9,0x1fc61e3e,
0x25eda7a8,0xa55f20a5,0xa2d7262f,0x273ba513,0x1cb2a5a8,0xa7ea25a8,0x27c3a764,0x9fc6a21f,0xa73b238b,0xa2d7270e,0x1648a513,0xa7fe262f,
0xa55f27d9,0x25ed9e3e,0xa7882472,0xa16426a7,0x241d1a46,0x26dda7f6,0xa4c427a8,0x266da0a5,0x164825a8,0x27fea5a8,0x22d7221f,0x273ba764,
0x27eaa62f,0x9cb2a513,0x26dda7a8,0xa41da0a5,0x9fc6a472,0xa7c326a7,0xa4c49e3e,0xa66d27d9,0xa788270e,0x2164238b,0xa5ed27f6,0x255f1a46,
0x9fc6a5a8,0xa7c325a8,0xa66d2764,0x24c4221f,0xa5ed27a8,0x255f20a5,0x273b9a46,0x22d7a7f6,0x27889e3e,0x2164a7d9,0x9648a6a7,0xa7fe2472,
0x9cb2a62f,0xa7ea2513,0xa6dd270e,0x241d238b,0x22d725a8,0x273ba5a8,0xa5eda21f,0xa55f2764,0x1fc6a7f6,0xa7c31a46,0x1cb2270e,0x27eaa38b,
0xa66d26a7,0x24c42472,0x241da7d9,0xa6dd9e3e,0x27fea0a5,0x1648a7a8,0xa7882513,0x2164262f,0xa4c4a5a8,0xa66d25a8,0x241da764,0xa6dda21f,
0x2164270e,0x2788a38b,0xa5ed262f,0x255f2513,0x9648a7d9,0xa7fe1e3e,0x273ba472,0xa2d7a6a7,0x9fc627f6,0x27c31a46,0xa7ea20a5,0x1cb227a8,
0x25ed25a8,0x255fa5a8,0x2788221f,0x2164a764,0xa66da513,0xa4c4262f,0xa7c3a0a5,0x9fc627a8,0x26dd2472,0x241da6a7,0x27ea1e3e,0x1cb2a7d9,
0xa73ba38b,0xa2d7270e,0xa7fe9a46,0x964827f6,0xa6dda5a8,0xa41d25a8,0x9cb22764,0x27ea221f,0x27fe20a5,0x1648a7a8,0xa164a7f6,0xa7881a46,
0xa73b1e3e,0x22d727d9,0x25ed26a7,0x255fa472,0x24c4a513,0xa66da62f,0xa7c3a38b,0x9fc6270e,0x278825a8,0x2164a5a8,0xa7fea21f,0x16482764,
0xa6dd1a46,0x241d27f6,0x24c4a38b,0xa66da70e,0x1cb2a6a7,0xa7eaa472,0x1fc627d9,0x27c31e3e,0x255f27a8,0x25eda0a5,0xa73ba62f,0xa2d72513,
0xa7eaa5a8,0x9cb225a8,0x9fc6a764,0xa7c3a21f,0x22d7a38b,0xa73ba70e,0x27fe2513,0x1648a62f,0x25ed27d9,0x255f9e3e,0xa1642472,0x278826a7,
0xa6dd9a46,0x241d27f6,0xa66da7a8,0xa4c420a5,0x27fe25a8,0x9648a5a8,0x273b221f,0xa2d7a764,0x1cb2262f,0x27ea2513,0x241d27a8,0x26dd20a5,
0xa7c3a472,0x1fc626a7,0xa66d9e3e,0x24c427d9,0xa164a70e,0xa788a38b,0xa55fa7f6,0xa5ed9a46,0xa7c3a5a8,0x1fc625a8,0x24c42764,0x266d221f,
0xa55fa7a8,0xa5eda0a5,0xa2d71a46,0x273b27f6,0x21649e3e,0xa788a7d9,0xa7fea6a7,0x16482472,0x27ea262f,0x9cb2a513,0xa41da70e,0xa6dda38b,
0x273b25a8,0xa2d7a5a8,0xa55fa21f,0x25ed2764,0x27c327f6,0x1fc69a46,0xa7eaa70e,0x1cb2238b,0x24c426a7,0x266d2472,0xa6dda7d9,0xa41d9e3e,
0x964820a5,0x27fe27a8,0xa164a513,0xa788a62f,0xa66da5a8,0x24c425a8,0xa6dda764,0xa41da21f,0xa788a70e,0x2164238b,0xa55fa62f,0xa5eda513,
0xa7fea7d9,0x16481e3e,0xa2d7a472,0xa73ba6a7,0xa7c3a7f6,0x9fc69a46,0x9cb2a0a5,0xa7eaa7a8,
};

#define PROF(slot) do {} while (0)
#define PROF3(slot) do {} while (0)
#define PROF2(slot) do {} while (0)

__device__ __forceinline__ uint32_t smem_u32(const void* p) { return (uint32_t)__cvta_generic_to_shared(p); }

__device__ __forceinline__ void mbar_init(uint32_t a, uint32_t c) {
  asm volatile("mbarrier.init.shared::cta.b64 [%0], %1;\n" ::"r"(a), "r"(c) : "memory");
}
__device__ __forceinline__ void mbar_expect_tx(uint32_t a, uint32_t bytes) {
  asm volatile("mbarrier.arrive.expect_tx.shared::cta.b64 _, [%0], %1;\n" ::"r"(a), "r"(bytes) : "memory");
}
__device__ __forceinline__ void mbar_arrive_cluster(uint32_t cluster_addr) {
  asm volatile("mbarrier.arrive.shared::cluster.b64 _, [%0];\n" ::"r"(cluster_addr) : "memory");
}
__device__ __forceinline__ void mbar_arrive_cluster_n(uint32_t cluster_addr, uint32_t n) {
  asm volatile("mbarrier.arrive.shared::cluster.b64 _, [%0], %1;\n" ::"r"(cluster_addr), "r"(n) : "memory");
}
__device__ __forceinline__ bool mbar_try(uint32_t a, uint32_t parity) {
  uint32_t ok;
  asm volatile("{\n.reg .pred p;\nmbarrier.try_wait.parity.shared::cta.b64 p, [%1], %2;\nselp.u32 %0, 1, 0, p;\n}\n"
               : "=r"(ok) : "r"(a), "r"(parity) : "memory");
  return ok;
}
__device__ __forceinline__ void mbar_wait(uint32_t a, uint32_t parity) {
  if (mbar_try(a, parity)) return;
#pragma unroll 1
  for (int n = 0; n < SPIN_LIMIT; n++)
    if (mbar_try(a, parity)) break;
}
__device__ __forceinline__ void mbar_wait_idle(uint32_t a, uint32_t parity) {
#pragma unroll 1
  for (int n = 0; n < SPIN_LIMIT; n++) {
    uint32_t ok;
    asm volatile("{\n.reg .pred p;\nmbarrier.try_wait.parity.shared::cta.b64 p, [%1], %2, %3;\nselp.u32 %0, 1, 0, p;\n}\n"
                 : "=r"(ok) : "r"(a), "r"(parity), "r"(4000) : "memory");
    if (ok) break;
  }
}
__device__ __forceinline__ bool elect_one() {
  uint32_t p;
  asm volatile("{\n.reg .pred P;\nelect.sync _|P, 0xffffffff;\nselp.u32 %0, 1, 0, P;\n}\n" : "=r"(p));
  return p;
}
__device__ __forceinline__ uint32_t mapa(uint32_t a, uint32_t rank) {
  uint32_t r;
  asm volatile("mapa.shared::cluster.u32 %0, %1, %2;\n" : "=r"(r) : "r"(a), "r"(rank));
  return r;
}
__device__ __forceinline__ void nb_sync(int id, int n) { asm volatile("bar.sync %0, %1;\n" ::"r"(id), "r"(n) : "memory"); }
__device__ __forceinline__ void nb_arrive(int id, int n) { asm volatile("bar.arrive %0, %1;\n" ::"r"(id), "r"(n) : "memory"); }
__device__ __forceinline__ void cluster_sync_all() {
  asm volatile("barrier.cluster.arrive.relaxed.aligned;\nbarrier.cluster.wait.aligned;\n" ::: "memory");
}
__device__ __forceinline__ void fence_async_smem() { asm volatile("fence.proxy.async.shared::cta;\n" ::: "memory"); }
__device__ __forceinline__ void fence_async_all() { asm volatile("fence.proxy.async.global;\n" ::: "memory"); }

__device__ __forceinline__ void tma_load_3d(uint32_t dst, const CUtensorMap* tm, uint32_t bar, int c0, int c1, int c2) {
  asm volatile(
      "cp.async.bulk.tensor.3d.shared::cluster.global.mbarrier::complete_tx::bytes [%0], [%1, {%3, %4, %5}], [%2];\n"
      ::"r"(dst), "l"(tm), "r"(bar), "r"(c0), "r"(c1), "r"(c2) : "memory");
}
__device__ __forceinline__ void tma_load_4d(uint32_t dst, const CUtensorMap* tm, uint32_t bar, int c0, int c1, int c2, int c3) {
  asm volatile(
      "cp.async.bulk.tensor.4d.shared::cluster.global.mbarrier::complete_tx::bytes [%0], [%1, {%3, %4, %5, %6}], [%2];\n"
      ::"r"(dst), "l"(tm), "r"(bar), "r"(c0), "r"(c1), "r"(c2), "r"(c3) : "memory");
}
__device__ __forceinline__ void tma_load_3d_mc(uint32_t dst, const CUtensorMap* tm, uint32_t bar, int c0, int c1, int c2) {
  asm volatile(
      "cp.async.bulk.tensor.3d.shared::cluster.global.mbarrier::complete_tx::bytes.multicast::cluster [%0], [%1, {%3, %4, %5}], [%2], %6;\n"
      ::"r"(dst), "l"(tm), "r"(bar), "r"(c0), "r"(c1), "r"(c2), "h"((uint16_t)3) : "memory");
}
__device__ __forceinline__ void tma_load_5d(uint32_t dst, const CUtensorMap* tm, uint32_t bar, int c0, int c4) {
  asm volatile(
      "cp.async.bulk.tensor.5d.shared::cluster.global.mbarrier::complete_tx::bytes [%0], [%1, {%3, %5, %5, %5, %4}], [%2];\n"
      ::"r"(dst), "l"(tm), "r"(bar), "r"(c0), "r"(c4), "r"(0) : "memory");
}
__device__ __forceinline__ void bulk_load(uint32_t dst, const void* src, uint32_t bytes, uint32_t bar) {
  asm volatile("cp.async.bulk.shared::cluster.global.mbarrier::complete_tx::bytes [%0], [%1], %2, [%3];\n"
               ::"r"(dst), "l"(src), "r"(bytes), "r"(bar) : "memory");
}
__device__ __forceinline__ void bulk_commit() { asm volatile("cp.async.bulk.commit_group;\n" ::: "memory"); }
__device__ __forceinline__ void bulk_wait0() { asm volatile("cp.async.bulk.wait_group 0;\n" ::: "memory"); }
__device__ __forceinline__ void prefetch_tmap(const CUtensorMap* tm) {
  asm volatile("prefetch.tensormap [%0];\n" ::"l"(tm) : "memory");
}

__device__ __forceinline__ void wg_fence() { asm volatile("wgmma.fence.sync.aligned;\n" ::: "memory"); }
__device__ __forceinline__ void wg_commit() { asm volatile("wgmma.commit_group.sync.aligned;\n" ::: "memory"); }
template <int N> __device__ __forceinline__ void wg_wait() {
  asm volatile("wgmma.wait_group.sync.aligned %0;\n" ::"n"(N) : "memory");
}
__device__ __forceinline__ uint64_t mkdesc(uint32_t addr, uint32_t lbo, uint32_t sbo, uint32_t swz) {
  return (uint64_t)((addr & 0x3FFFF) >> 4) | ((uint64_t)(lbo >> 4) << 16) | ((uint64_t)(sbo >> 4) << 32) |
         ((uint64_t)swz << 62);
}

#define R4(d, o) "+f"(d[o + 0]), "+f"(d[o + 1]), "+f"(d[o + 2]), "+f"(d[o + 3])
#define R8(d, o) R4(d, o), R4(d, o + 4)
#define R16(d, o) R8(d, o), R8(d, o + 8)
#define R32(d, o) R16(d, o), R16(d, o + 16)
#define R64(d, o) R32(d, o), R32(d, o + 32)

__device__ __forceinline__ void wgmma_n192(float (&d)[96], uint64_t da, uint64_t db, uint32_t acc) {
  asm volatile(
      "{\n.reg .pred p;\nsetp.ne.u32 p, %98, 0;\n"
      "wgmma.mma_async.sync.aligned.m64n192k16.f32.bf16.bf16 "
      "{%0,%1,%2,%3,%4,%5,%6,%7,%8,%9,%10,%11,%12,%13,%14,%15,%16,%17,%18,%19,%20,%21,%22,%23,%24,%25,%26,%27,%28,%29,%30,%31,"
      "%32,%33,%34,%35,%36,%37,%38,%39,%40,%41,%42,%43,%44,%45,%46,%47,%48,%49,%50,%51,%52,%53,%54,%55,%56,%57,%58,%59,%60,%61,%62,%63,"
      "%64,%65,%66,%67,%68,%69,%70,%71,%72,%73,%74,%75,%76,%77,%78,%79,%80,%81,%82,%83,%84,%85,%86,%87,%88,%89,%90,%91,%92,%93,%94,%95}, "
      "%96, %97, p, 1, 1, 0, 1;\n}\n"
      : R64(d, 0), R32(d, 64)
      : "l"(da), "l"(db), "r"(acc));
}
__device__ __forceinline__ void wgmma_n128(float (&d)[64], uint64_t da, uint64_t db, uint32_t acc) {
  asm volatile(
      "{\n.reg .pred p;\nsetp.ne.u32 p, %66, 0;\n"
      "wgmma.mma_async.sync.aligned.m64n128k16.f32.bf16.bf16 "
      "{%0,%1,%2,%3,%4,%5,%6,%7,%8,%9,%10,%11,%12,%13,%14,%15,%16,%17,%18,%19,%20,%21,%22,%23,%24,%25,%26,%27,%28,%29,%30,%31,"
      "%32,%33,%34,%35,%36,%37,%38,%39,%40,%41,%42,%43,%44,%45,%46,%47,%48,%49,%50,%51,%52,%53,%54,%55,%56,%57,%58,%59,%60,%61,%62,%63}, "
      "%64, %65, p, 1, 1, 0, 1;\n}\n"
      : R64(d, 0)
      : "l"(da), "l"(db), "r"(acc));
}
template <int N> __device__ __forceinline__ void fence_regs(float (&d)[N]) {
#pragma unroll
  for (int i = 0; i < N; i++) asm volatile("" : "+f"(d[i])::"memory");
}

__device__ __forceinline__ void mma16816(float (&d)[4], uint32_t a0, uint32_t a1, uint32_t a2, uint32_t a3, uint32_t b0,
                                         uint32_t b1) {
  asm("mma.sync.aligned.m16n8k16.row.col.f32.bf16.bf16.f32 {%0,%1,%2,%3}, {%4,%5,%6,%7}, {%8,%9}, {%0,%1,%2,%3};\n"
      : "+f"(d[0]), "+f"(d[1]), "+f"(d[2]), "+f"(d[3])
      : "r"(a0), "r"(a1), "r"(a2), "r"(a3), "r"(b0), "r"(b1));
}
__device__ __forceinline__ void mma16816_z(float (&d)[4], uint32_t a0, uint32_t a1, uint32_t a2, uint32_t a3, uint32_t b0,
                                           uint32_t b1) {
  asm("mma.sync.aligned.m16n8k16.row.col.f32.bf16.bf16.f32 {%0,%1,%2,%3}, {%4,%5,%6,%7}, {%8,%9}, {%10,%10,%10,%10};\n"
      : "=f"(d[0]), "=f"(d[1]), "=f"(d[2]), "=f"(d[3])
      : "r"(a0), "r"(a1), "r"(a2), "r"(a3), "r"(b0), "r"(b1), "f"(0.f));
}
__device__ __forceinline__ void ldsm4t(uint32_t (&r)[4], uint32_t a) {
  asm volatile("ldmatrix.sync.aligned.m8n8.x4.trans.shared.b16 {%0,%1,%2,%3}, [%4];\n"
               : "=r"(r[0]), "=r"(r[1]), "=r"(r[2]), "=r"(r[3]) : "r"(a) : "memory");
}
__device__ __forceinline__ void ldsm2t(uint32_t& r0, uint32_t& r1, uint32_t a) {
  asm volatile("ldmatrix.sync.aligned.m8n8.x2.trans.shared.b16 {%0,%1}, [%2];\n" : "=r"(r0), "=r"(r1) : "r"(a) : "memory");
}
__device__ __forceinline__ void st_async128(uint32_t a, uint32_t bar, uint32_t x, uint32_t y, uint32_t z, uint32_t w) {
  asm volatile("st.async.weak.shared::cluster.mbarrier::complete_tx::bytes.v4.b32 [%0], {%2,%3,%4,%5}, [%1];\n"
               ::"r"(a), "r"(bar), "r"(x), "r"(y), "r"(z), "r"(w) : "memory");
}
__device__ __forceinline__ void mbar_arrive(uint32_t a) {
  asm volatile("mbarrier.arrive.shared::cta.b64 _, [%0];\n" ::"r"(a) : "memory");
}
__device__ __forceinline__ void stsm4(uint32_t a, uint32_t r0, uint32_t r1, uint32_t r2, uint32_t r3) {
  asm volatile("stmatrix.sync.aligned.m8n8.x4.shared.b16 [%0], {%1,%2,%3,%4};\n"
               ::"r"(a), "r"(r0), "r"(r1), "r"(r2), "r"(r3) : "memory");
}
__device__ __forceinline__ void stsm4t(uint32_t a, uint32_t r0, uint32_t r1, uint32_t r2, uint32_t r3) {
  asm volatile("stmatrix.sync.aligned.m8n8.x4.trans.shared.b16 [%0], {%1,%2,%3,%4};\n"
               ::"r"(a), "r"(r0), "r"(r1), "r"(r2), "r"(r3) : "memory");
}
__device__ __forceinline__ uint2 lds64(uint32_t a) {
  uint2 v;
  asm volatile("ld.shared.v2.u32 {%0,%1}, [%2];\n" : "=r"(v.x), "=r"(v.y) : "r"(a));
  return v;
}
__device__ __forceinline__ uint4 lds128(uint32_t a) {
  uint4 v;
  asm volatile("ld.shared.v4.u32 {%0,%1,%2,%3}, [%4];\n" : "=r"(v.x), "=r"(v.y), "=r"(v.z), "=r"(v.w) : "r"(a) : "memory");
  return v;
}
__device__ __forceinline__ void sts128(uint32_t a, uint32_t x, uint32_t y, uint32_t z, uint32_t w) {
  asm volatile("st.shared.v4.u32 [%0], {%1,%2,%3,%4};\n" ::"r"(a), "r"(x), "r"(y), "r"(z), "r"(w) : "memory");
}
__device__ __forceinline__ uint32_t pack_bf16(float lo, float hi) {
  uint32_t r;
  asm("cvt.rn.bf16x2.f32 %0, %1, %2;\n" : "=r"(r) : "f"(hi), "f"(lo));
  return r;
}
__device__ __forceinline__ uint32_t bmul2(uint32_t a, uint32_t b) {
  uint32_t r;
  asm("mul.rn.bf16x2 %0, %1, %2;\n" : "=r"(r) : "r"(a), "r"(b));
  return r;
}
__device__ __forceinline__ uint32_t bmax2(uint32_t a, uint32_t b) {
  uint32_t r;
  asm("max.bf16x2 %0, %1, %2;\n" : "=r"(r) : "r"(a), "r"(b));
  return r;
}
__device__ __forceinline__ uint32_t bfma2(uint32_t a, uint32_t b, uint32_t c) {
  uint32_t r;
  asm("fma.rn.bf16x2 %0, %1, %2, %3;\n" : "=r"(r) : "r"(a), "r"(b), "r"(c));
  return r;
}
__device__ __forceinline__ void prefetch_l2(const void* p) { asm volatile("prefetch.global.L2 [%0];\n" ::"l"(p)); }
__device__ __forceinline__ void cp_async16n(uint32_t dst, const void* src) {
  asm volatile("cp.async.cg.shared.global [%0], [%1], 16;\n" ::"r"(dst), "l"(src) : "memory");
}
__device__ __forceinline__ void cp_async16(uint32_t dst, const void* src, uint32_t srcbytes) {
  asm volatile("cp.async.cg.shared.global.L2::256B [%0], [%1], 16, %2;\n" ::"r"(dst), "l"(src), "r"(srcbytes) : "memory");
}
__device__ __forceinline__ uint32_t ld_acquire(const uint32_t* p) {
  uint32_t v;
  asm volatile("ld.acquire.gpu.global.u32 %0, [%1];\n" : "=r"(v) : "l"(p) : "memory");
  return v;
}
__device__ __forceinline__ uint32_t ld_relaxed(const uint32_t* p) {
  uint32_t v;
  asm volatile("ld.relaxed.gpu.global.u32 %0, [%1];\n" : "=r"(v) : "l"(p) : "memory");
  return v;
}
__device__ __forceinline__ void st_release(uint32_t* p, uint32_t v) {
  asm volatile("st.release.gpu.global.u32 [%0], %1;\n" ::"l"(p), "r"(v) : "memory");
}
__device__ __forceinline__ void wait_flag(const uint32_t* p, uint32_t want) {
  int n = 0;
  while (ld_relaxed(p) != want && ++n < SPIN_LIMIT) __nanosleep(40);
  (void)ld_acquire(p);
}

struct Params {
  const __nv_bfloat16* x;
  const __nv_bfloat16* w;
  const __nv_bfloat16* q;
  const __nv_bfloat16* k;
  const __nv_bfloat16* v;
  const __nv_bfloat16* shift_k;
  const __nv_bfloat16* ssm_k;
  const __nv_bfloat16* ssm_D;
  const __nv_bfloat16* wo;
  __nv_bfloat16* out;
};

#define U4(c, d, o) c(d[o + 0]), c(d[o + 1]), c(d[o + 2]), c(d[o + 3])
#define U8(c, d, o) U4(c, d, o), U4(c, d, o + 4)
#define U16(c, d, o) U8(c, d, o), U8(c, d, o + 8)
#define U32(c, d, o) U16(c, d, o), U16(c, d, o + 16)
#define D32 "{%0,%1,%2,%3,%4,%5,%6,%7,%8,%9,%10,%11,%12,%13,%14,%15,%16,%17,%18,%19,%20,%21,%22,%23,%24,%25,%26,%27,%28,%29,%30,%31}"
#define D16 "{%0,%1,%2,%3,%4,%5,%6,%7,%8,%9,%10,%11,%12,%13,%14,%15}"
#define D8 "{%0,%1,%2,%3,%4,%5,%6,%7}"
template <int ACC> __device__ __forceinline__ void hmma_n128t(uint32_t (&d)[32], const uint32_t (&a)[4], uint64_t db) {
  if (ACC)
    asm volatile("wgmma.mma_async.sync.aligned.m64n128k16.f16.f16.f16 " D32 ", {%32,%33,%34,%35}, %36, 1, 1, 1, 1;\n"
                 : U32("+r", d, 0) : "r"(a[0]), "r"(a[1]), "r"(a[2]), "r"(a[3]), "l"(db));
  else
    asm volatile("wgmma.mma_async.sync.aligned.m64n128k16.f16.f16.f16 " D32 ", {%32,%33,%34,%35}, %36, 0, 1, 1, 1;\n"
                 : U32("=r", d, 0) : "r"(a[0]), "r"(a[1]), "r"(a[2]), "r"(a[3]), "l"(db));
}
template <int ACC, int TB> __device__ __forceinline__ void hmma_n32(uint32_t (&d)[8], const uint32_t (&a)[4], uint64_t db) {
  if (ACC)
    asm volatile("wgmma.mma_async.sync.aligned.m64n32k16.f16.f16.f16 " D8 ", {%8,%9,%10,%11}, %12, 1, 1, 1, %13;\n"
                 : U8("+r", d, 0) : "r"(a[0]), "r"(a[1]), "r"(a[2]), "r"(a[3]), "l"(db), "n"(TB));
  else
    asm volatile("wgmma.mma_async.sync.aligned.m64n32k16.f16.f16.f16 " D8 ", {%8,%9,%10,%11}, %12, 0, 1, 1, %13;\n"
                 : U8("=r", d, 0) : "r"(a[0]), "r"(a[1]), "r"(a[2]), "r"(a[3]), "l"(db), "n"(TB));
}
template <int ACC> __device__ __forceinline__ void hmma_n64t(uint32_t (&d)[16], const uint32_t (&a)[4], uint64_t db) {
  if (ACC)
    asm volatile("wgmma.mma_async.sync.aligned.m64n64k16.f16.f16.f16 " D16 ", {%16,%17,%18,%19}, %20, 1, 1, 1, 1;\n"
                 : U16("+r", d, 0) : "r"(a[0]), "r"(a[1]), "r"(a[2]), "r"(a[3]), "l"(db));
  else
    asm volatile("wgmma.mma_async.sync.aligned.m64n64k16.f16.f16.f16 " D16 ", {%16,%17,%18,%19}, %20, 0, 1, 1, 1;\n"
                 : U16("=r", d, 0) : "r"(a[0]), "r"(a[1]), "r"(a[2]), "r"(a[3]), "l"(db));
}
template <int N> __device__ __forceinline__ void fence_regs(uint32_t (&d)[N]) {
#pragma unroll
  for (int i = 0; i < N; i++) asm volatile("" : "+r"(d[i])::"memory");
}
__device__ __forceinline__ uint32_t hmul(uint32_t a, uint32_t b) { uint32_t r; asm("mul.rn.f16x2 %0, %1, %2;\n" : "=r"(r) : "r"(a), "r"(b)); return r; }
__device__ __forceinline__ uint32_t hfma(uint32_t a, uint32_t b, uint32_t c) { uint32_t r; asm("fma.rn.f16x2 %0, %1, %2, %3;\n" : "=r"(r) : "r"(a), "r"(b), "r"(c)); return r; }
__device__ __forceinline__ uint32_t hfnma(uint32_t a, uint32_t b, uint32_t c) {
  uint32_t r;
  asm("{\n.reg .b32 t;\nneg.f16x2 t, %1;\nfma.rn.f16x2 %0, t, %2, %3;\n}\n" : "=r"(r) : "r"(a), "r"(b), "r"(c));
  return r;
}
__device__ __forceinline__ uint32_t hrefl(uint32_t p, uint32_t s) {
  uint32_t r;
  asm("{\n.reg .b32 t;\nneg.f16x2 t, %2;\nfma.rn.f16x2 %0, %1, %3, t;\n}\n" : "=r"(r) : "r"(p), "r"(s), "r"(0x40004000u));
  return r;
}
__device__ __forceinline__ void bfly(uint32_t xr, uint32_t xi, uint32_t tr, uint32_t ti, uint32_t yr, uint32_t yi, uint32_t ur,
                                     uint32_t ui, uint32_t& sr, uint32_t& si, uint32_t& dr, uint32_t& di) {
  const uint32_t pr = hfnma(xi, ti, hmul(xr, tr)), pi = hfma(xi, tr, hmul(xr, ti));
  sr = hfnma(yi, ui, hfma(yr, ur, pr));
  si = hfma(yi, ur, hfma(yr, ui, pi));
  dr = hrefl(pr, sr);
  di = hrefl(pi, si);
}
template <int BH> __device__ __forceinline__ void fft_e1(const uint32_t (&d)[32], const uint32_t (&tw)[16], uint32_t (&a2)[2][2][4]) {
#pragma unroll
  for (int be = 0; be < 2; be++)
#pragma unroll
    for (int s = 0; s < 2; s++) {
      const int o = 16 * s + 8 * be + 2 * BH, p = 2 * BH;
      bfly(d[o], d[o + 1], tw[p], tw[p + 1], d[o + 4], d[o + 5], tw[p + 4], tw[p + 5], a2[be][0][s], a2[be][0][2 + s],
           a2[be][1][s], a2[be][1][2 + s]);
    }
}
__device__ __forceinline__ uint32_t hfms(uint32_t a, uint32_t b, uint32_t c) {
  uint32_t r;
  asm("{\n.reg .b32 t;\nneg.f16x2 t, %3;\nfma.rn.f16x2 %0, %1, %2, t;\n}\n" : "=r"(r) : "r"(a), "r"(b), "r"(c));
  return r;
}
template <int C, int J> __device__ __forceinline__ void fft_e2(const uint32_t (&d0)[8], const uint32_t (&d1)[8], uint32_t (&a3)[2][4]) {
  const uint32_t ur = d0[2 * J], ui = d0[4 + 2 * J], hr = d0[2 * J + 1], hi = d0[5 + 2 * J];
  const uint32_t vr = d1[2 * J], vi = d1[4 + 2 * J], gr = d1[2 * J + 1], gi = d1[5 + 2 * J];
  const uint32_t pr = hfnma(ui, hi, hmul(ur, hr)), pi = hfma(ui, hr, hmul(ur, hi));
  a3[0][2 + C] = pr;
  a3[0][C] = pi;
  a3[1][2 + C] = hfnma(vi, hi, hfma(vr, hr, hfnma(ui, gi, hfms(ur, gr, pi))));
  a3[1][C] = hfma(vi, hr, hfma(vr, hi, hfma(ui, gr, hfma(ur, gi, pr))));
}
__device__ __forceinline__ void fft_e3(const uint32_t (&d)[2][8], const uint32_t (&tw)[16], uint32_t zaddr) {
#pragma unroll
  for (int rho = 0; rho < 2; rho++) {
    uint32_t zr[4], zi[4];
#pragma unroll
    for (int nb = 0; nb < 4; nb++) {
      const uint32_t xi = d[nb >> 1][2 * (nb & 1) + rho], xr = d[nb >> 1][4 + 2 * (nb & 1) + rho];
      const uint32_t tr = tw[8 + 4 * rho + 2 * (nb & 1)], ti = tw[9 + 4 * rho + 2 * (nb & 1)];
      zr[nb] = hfnma(xi, ti, hmul(xr, tr));
      zi[nb] = hfma(xi, tr, hmul(xr, ti));
    }
    stsm4(zaddr + rho * 2048, zr[0], zr[1], zr[2], zr[3]);
    stsm4(zaddr + rho * 2048 + 1024, zi[0], zi[1], zi[2], zi[3]);
  }
}
__device__ __forceinline__ float bf_lo(uint32_t v) {
  uint32_t r;
  asm("prmt.b32 %0, %1, 0, 0x1044;\n" : "=r"(r) : "r"(v));
  return __uint_as_float(r);
}
__device__ __forceinline__ float bf_hi(uint32_t v) { return __uint_as_float(v & 0xffff0000u); }
__device__ __forceinline__ float ex2(float x) {
  float r;
  asm("ex2.approx.ftz.f32 %0, %1;\n" : "=f"(r) : "f"(x));
  return r;
}
__device__ __forceinline__ float rcp(float x) {
  float r;
  asm("rcp.approx.ftz.f32 %0, %1;\n" : "=f"(r) : "f"(x));
  return r;
}

__device__ __forceinline__ int g2_a(int s) { return ((0xA1054 >> (4 * s)) & 15) * 16384; }
__device__ __forceinline__ int g2_b(int s) { return ((0xCDB32 >> (4 * s)) & 15) * 16384; }
static_assert(OFF_U == 10 * 16384 && OFF_H == 12 * 16384 && OFF_OP == 4 * 16384, "units");
__device__ __forceinline__ int g2_k(int hp, int i) {
  return i < 2 ? hp ^ 1 ^ i : i < 4 ? (hp & ~1) ^ i : ((hp & ~3) + i) & 15; }
__device__ __forceinline__ int y_slot(int wg, int it) {
  static_assert(T_B2 == T_TW + 8192 && T_A1 == T_B2 + 4096, "y slots");
  return OFF_T + T_TW + ((it + 3) & 3) * 4096 + wg * 2048;
}

__device__ __forceinline__ void to_arr(uint32_t (&d)[4], uint4 v) { d[0] = v.x; d[1] = v.y; d[2] = v.z; d[3] = v.w; }

__device__ __forceinline__ void attn_stage(uint32_t sb, int blk, int lane, const float (&acc)[96], uint32_t (&k1)[2][4]) {
  const int lr = lane & 7, lm = lane >> 3;
  const uint32_t base = sb + OFF_VP + (blk * 16 + lr + 8 * (lm & 1)) * 128;
#pragma unroll
  for (int i = 0; i < 8; i++) k1[i >> 2][i & 3] = pack_bf16(acc[34 + 4 * i], acc[35 + 4 * i]);
  const uint32_t kh = sb + OFF_KH + blk * 2048 + lane * 16;
  sts128(kh, k1[0][0], k1[0][1], k1[0][2], k1[0][3]);
  sts128(kh + 512, k1[1][0], k1[1][1], k1[1][2], k1[1][3]);
#pragma unroll
  for (int j = 0; j < 8; j += 2)
    stsm4(base + (((j + (lm >> 1)) ^ lr) << 4), pack_bf16(acc[64 + 4 * j], acc[65 + 4 * j]),
          pack_bf16(acc[66 + 4 * j], acc[67 + 4 * j]), pack_bf16(acc[68 + 4 * j], acc[69 + 4 * j]),
          pack_bf16(acc[70 + 4 * j], acc[71 + 4 * j]));
}
__device__ __forceinline__ void attn_pack(const float (&acc)[96], uint32_t (&qa)[2][8], uint32_t (&k0)[2][4]) {
#pragma unroll
  for (int hd = 0; hd < 2; hd++) {
#pragma unroll
    for (int i = 0; i < 8; i++) {
      asm volatile("cvt.rn.bf16x2.f32 %0, %1, %2;\n" : "=r"(qa[hd][i]) : "f"(acc[16 * hd + 2 * i + 1]), "f"(acc[16 * hd + 2 * i]));
    }
#pragma unroll
    for (int i = 0; i < 4; i++) {
      asm volatile("cvt.rn.bf16x2.f32 %0, %1, %2;\n" : "=r"(k0[hd][i]) : "f"(acc[33 + 16 * hd + 4 * i]), "f"(acc[32 + 16 * hd + 4 * i]));
    }
  }
}
__device__ __forceinline__ void attn_own(const uint32_t (&k0)[2][4], const uint32_t (&k1)[2][4], bool le0, bool le1,
                                         const uint32_t (&qa)[2][8], float (&l)[2][4]) {
#pragma unroll
  for (int hd = 0; hd < 2; hd++) {
    float s0[4], s1[4];
    mma16816_z(s0, qa[hd][0], qa[hd][1], qa[hd][2], qa[hd][3], k0[hd][0], k0[hd][1]);
    mma16816_z(s1, qa[hd][0], qa[hd][1], qa[hd][2], qa[hd][3], k1[hd][0], k1[hd][1]);
    mma16816(s0, qa[hd][4], qa[hd][5], qa[hd][6], qa[hd][7], k0[hd][2], k0[hd][3]);
    mma16816(s1, qa[hd][4], qa[hd][5], qa[hd][6], qa[hd][7], k1[hd][2], k1[hd][3]);
    l[hd][0] = s0[0];
    l[hd][1] = s0[1];
    l[hd][2] = le0 ? s1[2] : s0[2];
    l[hd][3] = le1 ? s1[3] : s0[3];
  }
}
template <int N> __device__ __forceinline__ void quad_softmax(float (&x)[N][2], uint32_t (&pp)[N]) {
  const float c2 = 1.4426950408889634f;
  uint32_t q[N], mx[N / 2];
#pragma unroll
  for (int n = 0; n < N; n++) {
    const uint32_t r = pack_bf16(x[n][0], x[n][1]);
    q[n] = bfma2(r, 0x3e353e35u, bmul2(r, 0x379e379eu));
    x[n][0] = bf_lo(q[n]);
    x[n][1] = bf_hi(q[n]);
  }
#pragma unroll
  for (int n = 0; n < N / 2; n++)
    mx[n] = bmax2(__byte_perm(q[2 * n], q[2 * n + 1], 0x5410), __byte_perm(q[2 * n], q[2 * n + 1], 0x7632));
#pragma unroll
  for (int o = 1; o <= 2; o++)
#pragma unroll
    for (int n = 0; n < N / 2; n++) mx[n] = bmax2(mx[n], __shfl_xor_sync(0xffffffffu, mx[n], o));
  float m[N], t[N];
#pragma unroll
  for (int n = 0; n < N / 2; n++) {
    m[2 * n] = bf_lo(mx[n]);
    m[2 * n + 1] = bf_hi(mx[n]);
  }
#pragma unroll
  for (int n = 0; n < N; n++) {
    const float nm = -m[n] * c2;
    x[n][0] = ex2(fmaf(x[n][0], c2, nm));
    x[n][1] = ex2(fmaf(x[n][1], c2, nm));
    t[n] = x[n][0] + x[n][1];
  }
#pragma unroll
  for (int o = 1; o <= 2; o++)
#pragma unroll
    for (int n = 0; n < N; n++) t[n] += __shfl_xor_sync(0xffffffffu, t[n], o);
#pragma unroll
  for (int n = 0; n < N; n++) {
    const float inv = rcp(t[n]);
    pp[n] = pack_bf16(x[n][0] * inv, x[n][1] * inv);
  }
}
__device__ __forceinline__ void attn_pv(uint32_t dst, const uint32_t (&va)[4], const uint32_t (&vb)[4], uint32_t pp,
                                        uint32_t maskLE) {
  const uint32_t b0 = pp & ~maskLE, b1 = pp & maskLE;
  float oa[4], ob[4];
  mma16816_z(oa, va[0], va[1], va[2], va[3], b0, b1);
  mma16816_z(ob, vb[0], vb[1], vb[2], vb[3], b0, b1);
  stsm4t(dst, pack_bf16(oa[0], oa[1]), pack_bf16(oa[2], oa[3]), pack_bf16(ob[0], ob[1]), pack_bf16(ob[2], ob[3]));
}

template <int MODE>
__global__ void __cluster_dims__(2, 1, 1) __launch_bounds__(NTHREADS, 1)
fused_kernel(const Params p, const __grid_constant__ CUtensorMap tmX, const __grid_constant__ CUtensorMap tmW,
             const __grid_constant__ CUtensorMap tmWo,
             const __grid_constant__ CUtensorMap tmQ,
             const __grid_constant__ CUtensorMap tmXh, const __grid_constant__ CUtensorMap tmWh) {
  extern __shared__ __align__(1024) uint8_t smem[];
  const uint32_t sb = smem_u32(smem) + HALO;
  const uint32_t bars = sb + OFF_BAR;
  const int tid = threadIdx.x, lane = tid & 31, warp = __shfl_sync(0xffffffffu, tid >> 5, 0);
  const int rank = blockIdx.x & 1;
  const bool halo_cta = blockIdx.x < 4;
  if (halo_cta && MODE != 0) return;
  int grp, mem;
  {
    const int t = (blockIdx.x >> 1) - 4, u = t - 32;
    const int q7 = (u * 37) >> 8;
    const bool lo = (unsigned)t < 32u, mid = (unsigned)u < 28u;
    grp = lo ? (t & 7) : (mid ? 1 + u - 7 * q7 : 0);
    mem = lo ? (t >> 3) : (mid ? 4 + q7 : (t < 0 ? t + 6 : t - 54));
  }
  const int rg = (grp >> 2) * 4 + (mem >> 1), hp = (grp & 3) * 4 + (mem & 1) * 2 + rank;
  const int rb2 = (grp >> 2) * 8 + mem, cb2 = (grp & 3) * 2 + rank;
  const int chb = grp * 16 + mem * 2 + rank;
  const int cta = rg * 16 + hp;
  const int par = rg >> 2, gidx = rg & 3;

  if (tid < 256 && !halo_cta && MODE != 2) {
    const int r = tid >> 3, c = tid & 7;
    const uint32_t so = r * 128 + ((c ^ (r & 7)) << 4);
    const __nv_bfloat16* wg0 = p.w + (size_t)r * (3 * DM) + hp * 64 + c * 8;
    const __nv_bfloat16* xg0 = p.x + (size_t)(2 * (gidx * 256 + r) + par) * DM + c * 8;
#pragma unroll
    for (int j = 0; j < 3; j++) cp_async16n(sb + OFF_1B + j * 4096 + so, wg0 + j * DM);
#pragma unroll
    for (int i = 0; i < 8; i++) cp_async16n(sb + i * 4096 + so, xg0 + (size_t)i * 64 * DM);
    asm volatile("cp.async.commit_group;\n" ::: "memory");
  }
  if (tid == 256) {
    prefetch_tmap(halo_cta ? &tmXh : &tmX);
#pragma unroll
    for (int i = 0; i < NS1B; i++) mbar_init(bars + 8 * (BAR_FULLB + i), 1);
#pragma unroll
    for (int i = 0; i < NS1A; i++) mbar_init(bars + 8 * (BAR_FULLA + i), 1);
    asm volatile("fence.mbarrier_init.release.cluster;\n" ::: "memory");
    if (!halo_cta && MODE != 2) {
      mbar_expect_tx(bars + 8 * (BAR_FULLB + 1), STG1B);
      tma_load_3d(sb + OFF_1B + 1 * STG1B, &tmW, bars + 8 * (BAR_FULLB + 1), hp * 64, 32, 0);
      mbar_expect_tx(bars + 8 * (BAR_FULLB + 2), STG1B);
      tma_load_3d(sb + OFF_1B + 2 * STG1B, &tmW, bars + 8 * (BAR_FULLB + 2), hp * 64, 64, 0);
    } else {
      prefetch_tmap(&tmWh);
    }
  } else if (tid == 288) {
#pragma unroll
    for (int i = 0; i < NS1A; i++) mbar_init(bars + 8 * (BAR_EMPTYA + i), 4);
#pragma unroll
    for (int i = 0; i < NS1B; i++) mbar_init(bars + 8 * (BAR_EMPTYB + i), 2);
    asm volatile("fence.mbarrier_init.release.cluster;\n" ::: "memory");
  } else if (tid == 320) {
#pragma unroll
    for (int i = 0; i < NS2; i++) {
      mbar_init(bars + 8 * (BAR_FULL2 + i), 1);
      mbar_init(bars + 8 * (BAR_EMPTY2 + i), 4);
    }
    mbar_init(bars + 8 * BAR_DEAD, 2);
    mbar_init(bars + 8 * (BAR_DEAD + 1), 2);
    mbar_init(bars + 8 * BAR_X, 2);
    mbar_init(bars + 8 * BAR_REL, 2);
    asm volatile("fence.mbarrier_init.release.cluster;\n" ::: "memory");
  } else if (tid == 352) {
    mbar_init(bars + 8 * BAR_T, 1);
    mbar_init(bars + 8 * BAR_UH, 3);
    mbar_init(bars + 8 * BAR_LFREE, 4);
    mbar_init(bars + 8 * BAR_LAND, 1);
    mbar_init(bars + 8 * BAR_U, 1);
    mbar_init(bars + 8 * BAR_Q, 1);
    mbar_init(bars + 8 * BAR_STG, 9);
    asm volatile("fence.mbarrier_init.release.cluster;\n" ::: "memory");
  }
  if (warp == 8) PROF2(23);
  cluster_sync_all();
  if (warp == 8) PROF2(24);

  if (warp >= 8) {
    const int hw = warp - 8;
    const int lr = lane & 7, lm = lane >> 3;
    auto g1_issue_a = [&](int j, int s) {
      const uint32_t fb = bars + 8 * (BAR_FULLA + s);
      mbar_expect_tx(fb, STG1A);
      tma_load_3d_mc(sb + s * STG1A + rank * 16384, &tmX, fb, j * 64, par, gidx * 256 + rank * 128);
    };
    auto g1_issue_b = [&](int kb, int s) {
      const uint32_t fb = bars + 8 * (BAR_FULLB + s);
      mbar_expect_tx(fb, STG1B);
      tma_load_3d(sb + OFF_1B + s * STG1B, &tmW, fb, hp * 64, kb * 32, 0);
    };
    asm volatile("setmaxnreg.dec.sync.aligned.u32 %0;\n" :: "n"(REG_HELP));

    if (halo_cta) {
      if (hw == 0) {
        int s = 0, ph = 1;
#pragma unroll 1
        for (int kb = 0; kb < 16; kb++) {
          mbar_wait(bars + 8 * (BAR_EMPTYB + s), ph);
          const uint32_t fb = bars + 8 * (BAR_FULLB + s), st = sb + s * STGH;
          if (elect_one()) {
            mbar_expect_tx(fb, STGH);
            tma_load_4d(st, &tmXh, fb, kb * 64, 248, 0, 0);
            tma_load_3d(st + 8192, &tmWh, fb, 0, kb * 64, 16 + blockIdx.x * 4);
            tma_load_3d(st + 8192 + 32768, &tmWh, fb, 0, kb * 64, 32 + blockIdx.x * 4);
          }
          if (++s == 3) { s = 0; ph ^= 1; }
        }
      }
      __syncwarp();
    } else if (hw == 0) {
      uint32_t epoch = 0;
      if (lane < (MODE == 2 ? NS2 : 2)) mbar_arrive_cluster_n(mapa(bars, rank) + 8 * (BAR_EMPTY2 + lane), 4);
      if (MODE != 2) {
      epoch = ld_relaxed(g_flag_o + 2 * cta) + 1;
      if (lane == 0) {
        mbar_expect_tx(bars + 8 * BAR_U, 32768);
        mbar_expect_tx(bars + 8 * BAR_LAND, 32768 + 64);
        mbar_expect_tx(bars + 8 * BAR_Q, 32768);
        mbar_expect_tx(bars + 8 * BAR_T, T_END);
      }
      {
        int sa = 1, pha = 1, sbb = 2, phb = 1;
#pragma unroll 1
        for (int kb = 2; kb < 32; kb++) {
          if (!(kb & 1)) {
            mbar_wait(bars + 8 * (BAR_EMPTYA + sa), pha);
            if (elect_one()) g1_issue_a(kb >> 1, sa);
            if (++sa == NS1A) { sa = 0; pha ^= 1; }
          }
          mbar_wait(bars + 8 * (BAR_EMPTYB + sbb), phb);
          if (kb > 2 && elect_one()) g1_issue_b(kb, sbb);
          __syncwarp();
          if (kb >= PF0 && kb < PF0 + 12)
            prefetch_l2((kb < PF0 + 8 ? p.q + (size_t)chb * 16384 + (kb - PF0) * 2048 : p.wo + (size_t)chb * 8192 + (kb - PF0 - 8) * 2048) + lane * 64);
          if (kb == 4) PROF2(27);
          if (kb == 1) PROF2(38);
          if (kb == 2) PROF2(39);
          if (++sbb == NS1B) { sbb = 0; phb ^= 1; }
        }
      }
      static_assert(32 % NS1B == 2 && (32 / NS1B) % 2 == 0 && OFF_Q == OFF_1B && 2 * STG1B == 6 * 4096, "slots / parity of these loads");
      const uint8_t* tab = reinterpret_cast<const uint8_t*>(g_tab);
      if (lane == 0) {
        prefetch_tmap(&tmWo);
        prefetch_tmap(&tmQ);
        bulk_load(sb + OFF_T + T_A1, tab + T_A1, T_END - T_A1, bars + 8 * BAR_T);
        mbar_wait(bars + 8 * (BAR_EMPTYB + 2), 1);
        tma_load_5d(sb + OFF_Q + 6 * 4096, &tmQ, bars + 8 * BAR_Q, (chb & ~1) * 8, rank * 32 + 24);
        tma_load_5d(sb + OFF_Q + 7 * 4096, &tmQ, bars + 8 * BAR_Q, (chb & ~1) * 8, rank * 32 + 28);
        if (gidx != 0) wait_flag(g_flag_h + (hp >> 2), epoch);
      }
      __syncwarp();
      {
        uint4 hk0 = make_uint4(0, 0, 0, 0), hk1 = hk0, hv0 = hk0, hv1 = hk0;
        if (gidx != 0) {
          const uint4* src = g_halo + cta * 128 + lane;
          hk0 = __ldcg(src); hk1 = __ldcg(src + 32); hv0 = __ldcg(src + 64); hv1 = __ldcg(src + 96);
        }
        if (lane == 0) {
          mbar_wait(bars + 8 * (BAR_EMPTYB + 3), 1);
          bulk_load(sb + OFF_T, tab, T_TW, bars + 8 * BAR_T);
        }
        __syncwarp();
        PROF2(18);
        sts128(sb - HALO + lane * 16, hk0.x, hk0.y, hk0.z, hk0.w);
        sts128(sb - HALO + 512 + lane * 16, hk1.x, hk1.y, hk1.z, hk1.w);
        stsm4(sb - HALO + 1024 + lr * 128 + ((lm ^ lr) << 4), hv0.x, hv0.y, hv0.z, hv0.w);
        stsm4(sb - HALO + 1024 + lr * 128 + (((4 + lm) ^ lr) << 4), hv1.x, hv1.y, hv1.z, hv1.w);
        __syncwarp();
        if (lane == 0) {
          mbar_arrive(bars + 8 * BAR_STG);
          mbar_wait(bars + 8 * (BAR_EMPTYB + 4), 1);
          bulk_load(sb + OFF_T + T_TW, tab + T_TW, T_A1 - T_TW, bars + 8 * BAR_T);
          mbar_wait(bars + 8 * BAR_EMPTYB, 0);
#pragma unroll 1
          for (int i = 0; i < 6; i++) tma_load_5d(sb + OFF_Q + i * 4096, &tmQ, bars + 8 * BAR_Q, (chb & ~1) * 8, rank * 32 + i * 4);
        }
        __syncwarp();
      }
      }
      if (MODE != 1) {
        auto korder = [&](int i) { return MODE == 2 ? i : g2_k(hp, i); };
        const __nv_bfloat16* osrc = g_o + (size_t)(rb2 >> 1) * 16 * 16384 + ((rb2 & 1) * 2 + rank) * 4096;
        const uint32_t* flag = g_flag_o + ((rb2 >> 1) * 32 + korder(lane & 15) * 2 + (rb2 & 1));
        uint32_t ready = MODE == 0 ? 0u : ~0u, pv = 0;
        const __nv_bfloat16* o23[2] = {osrc + korder(2) * 16384, osrc + korder(3) * 16384};
        if (MODE == 0) {
          asm volatile("" : "+l"(o23[0]), "+l"(o23[1]), "+l"(flag));
          if (lane < 4 && lane != 1) mbar_expect_tx(bars + 8 * (BAR_FULL2 + lane), STG2);
          mbar_wait_idle(bars + 8 * (BAR_EMPTY2 + 2), 0);
          mbar_wait(bars + 8 * (BAR_EMPTY2 + 3), 0);
          mbar_wait_idle(bars + 8 * BAR_REL, 0);
          if (elect_one()) {
            tma_load_3d(sb + g2_b(0), &tmWo, bars + 8 * BAR_FULL2, 0, korder(0) * 64, cb2 * 2);
            tma_load_3d(sb + g2_b(1), &tmWo, bars + 8 * (BAR_FULL2 + 1), 0, korder(1) * 64, cb2 * 2);
          }
        }
#pragma unroll
        for (int i = MODE == 0 ? 2 : 0; i < 16; i++) {
          const int kb = korder(i), s = i % NS2, ph = (i / NS2) & 1;
          const uint32_t fb = bars + 8 * (BAR_FULL2 + s);
          if (!((ready >> i) & 1)) {
            int n = 0;
            do {
              ready |= __ballot_sync(0xffffffffu, ld_acquire(flag) == epoch);
            } while (!((ready >> i) & 1) && ++n < SPIN_LIMIT);
            fence_async_all();
          }
          if (i == 2) PROF(21);
          const bool pre = MODE == 0 && i < 4;
          if (!pre) mbar_wait(bars + 8 * (BAR_EMPTY2 + s), ph);
          if (elect_one()) {
            if (!pre) mbar_expect_tx(fb, STG2);
            asm volatile(
                "cp.async.bulk.shared::cluster.global.mbarrier::complete_tx::bytes.multicast::cluster [%0], [%1], %2, [%3], %4;\n"
                ::"r"(sb + g2_a(s) + rank * 8192), "l"(pre ? o23[i & 1] : osrc + kb * 16384), "r"(8192), "r"(fb), "h"((uint16_t)3) : "memory");
            if (!pre) tma_load_3d(sb + g2_b(s), &tmWo, fb, 0, kb * 64, cb2 * 2);
          }
          if (MODE == 0 && i == 3) pv = ld_relaxed(flag);
          if (MODE == 0 && i == 4) {
            ready |= __ballot_sync(0xffffffffu, pv == epoch);
            asm volatile("fence.acquire.gpu;\n" ::: "memory");
            fence_async_all();
          }
          if (i == 3) PROF(37);

        }
      }
      __syncwarp();
    } else if (MODE != 2) {
      {
        const int g = lane >> 2, t = lane & 3;
        uint32_t w[2][4];
#pragma unroll
        for (int h = 0; h < 2; h++) {
          const uint2 x = __ldg(reinterpret_cast<const uint2*>(p.shift_k + ((chb & ~1) * 8 + h * 8 + g) * 4));
          w[h][0] = __byte_perm(x.x, x.x, 0x1010);
          w[h][1] = __byte_perm(x.x, x.x, 0x3232);
          w[h][2] = __byte_perm(x.y, x.y, 0x1010);
          w[h][3] = __byte_perm(x.y, x.y, 0x3232);
        }
        auto swz = [](int r) { return (((r & 29) | ((r ^ (r >> 2)) & 2)) << 5) | (r & 16); };
        const uint32_t kring = sb + OFF_H + (hw - 1) * 8192, vring = kring + 4096;
        const int s0 = rank * 32 + (hw - 1) * 11, s1 = hw == 3 ? rank * 32 + 32 : s0 + 11;
        const size_t goff = (size_t)(lane >> 1) * DM + (chb & ~1) * 8 + (lane & 1) * 8;
        const __nv_bfloat16* kg = p.k + goff;
        const __nv_bfloat16* vg = p.v + goff;
        const uint32_t d0 = swz(lane >> 1) ^ ((lane & 1) << 4), d1 = swz(16 + (lane >> 1)) ^ ((lane & 1) << 4);
        auto issue = [&](int st) {
          const uint32_t so = (st & 3) << 10;
          cp_async16(kring + so + d0, kg + (size_t)st * 32 * DM, 16);
          cp_async16(kring + so + d1, kg + (size_t)(st * 32 + 16) * DM, 16);
          cp_async16(vring + so + d0, vg + (size_t)st * 32 * DM, 16);
          cp_async16(vring + so + d1, vg + (size_t)(st * 32 + 16) * DM, 16);
        };
        const int xa = 8 * (lr >> 1) + 2 * lm + (lr & 1), xb = 8 * (lr >> 1) - 4 + 2 * (lm & 1) + (lr & 1);
        const uint32_t la = swz(xa), lb = swz(xb & 31);
        const int backb = xb < 0 ? 1 : 0;
        const uint32_t ud[2] = {mapa(sb + OFF_U + g * 4096 + t * 16, 0), mapa(sb + OFF_U + g * 4096 + t * 16, 1)};
        const uint32_t ub[2] = {mapa(bars + 8 * BAR_U, 0), mapa(bars + 8 * BAR_U, 1)};
        if (lane == 0) mbar_wait(bars + 8 * (BAR_FULLB + NS1B - 1), 0);
        __syncwarp();
        if (lane >= 24) cp_async16(kring + (((s0 - 1) & 3) << 10) + d1, s0 > 0 ? kg + (size_t)(s0 * 32 - 16) * DM : kg, s0 > 0 ? 16 : 0);
        issue(s0);
        asm volatile("cp.async.commit_group;\n" ::: "memory");
        issue(s0 + 1);
        asm volatile("cp.async.commit_group;\n" ::: "memory");
#pragma unroll 1
        for (int st = s0; st < s1; st++) {
          if (st + 2 < s1) issue(st + 2);
          if (hw == 1 && st - s0 < 8) prefetch_l2(p.ssm_k + (size_t)(chb * 8 + st - s0) * SEQ + lane * 64);
          if (hw == 2 && st == s0 + 4 && lane < 2) prefetch_l2(g_tab + (chb * 2 + lane) * 32);
          const uint32_t uo = (st ^ ((g ^ (st >> 2)) & 1)) * 64;
          asm volatile("cp.async.commit_group;\n" ::: "memory");
          asm volatile("cp.async.wait_group 2;\n" ::: "memory");
          __syncwarp();
#pragma unroll
          for (int h = 0; h < 2; h++) {
            uint32_t e[6], vv[4], e4[4];
            ldsm4t(e4, kring + ((st & 3) << 10) + (la ^ (h << 4)));
            ldsm2t(e[0], e[1], kring + (((st - backb) & 3) << 10) + (lb ^ (h << 4)));
            ldsm4t(vv, vring + ((st & 3) << 10) + (la ^ (h << 4)));
            e[2] = e4[0]; e[3] = e4[1]; e[4] = e4[2]; e[5] = e4[3];
            uint32_t o[5];
#pragma unroll
            for (int i = 0; i < 5; i++) o[i] = __byte_perm(e[i], e[i + 1], 0x5432);
#pragma unroll
            for (int i = 0; i < 4; i++) {
              uint32_t a = bmul2(o[i], w[h][3]);
              a = bfma2(e[i + 1], w[h][2], a);
              a = bfma2(o[i + 1], w[h][1], a);
              a = bfma2(e[i + 2], w[h][0], a);
              vv[i] = bmul2(a, vv[i]);
            }
            st_async128(ud[h] + uo, ub[h], vv[0], vv[1], vv[2], vv[3]);
          }
          __syncwarp();
        }
        PROF(16);
      }
      {
        const int rw = (lane >> 3) + (lane & 4), ck = lane & 3;
        const uint32_t so = rw * 64 + ck * 16, dof = rw * 128 + ((ck ^ rw) << 4);
        const uint8_t* hsrc = reinterpret_cast<const uint8_t*>(p.ssm_k + (size_t)chb * 8 * SEQ) + so;
        const float dv = lane < 8 ? __bfloat162float(p.ssm_D[chb * 8 + lane]) : 0.f;
        uint32_t x[32];
        auto load = [&](const uint8_t* src, int i) {
          asm volatile("ld.v4.u32 {%0,%1,%2,%3}, [%4];\n" : "=r"(x[4 * i]), "=r"(x[4 * i + 1]), "=r"(x[4 * i + 2]), "=r"(x[4 * i + 3])
                       : "l"(src + i * 512) : "memory");
        };
#pragma unroll
        for (int i = 0; i < 8; i++) load(hsrc + (hw - 1) * 4096, i);
        nb_sync(NB_HELP3, 96);
        mbar_wait(bars + 8 * BAR_U, 0);
        int eh = 0;
#pragma unroll 1
        for (int n = 2 * (hw - 1); n < 16; n += (n & 1) ? 5 : 1) {
          const int c = n >> 1;
          const uint8_t* nsrc = (n & 1) ? hsrc + (c < 5 ? c + 3 : c) * 4096
                                        : smem + HALO + OFF_U + c * 4096 + (so ^ (((c ^ (lane >> 2)) & 1) << 6));
          const uint32_t dst = sb + ((n & 1) ? OFF_U : OFF_H) + c * 4096 + dof;
          const float dc = __shfl_sync(0xffffffffu, dv, c);
          const float h0 = bf_lo(x[0]) + ((lane | (n & 1)) == 0 ? dc : 0.f), h1 = bf_hi(x[0]);
          x[0] = pack_bf16(h0, h1);
          uint32_t m[2] = {x[0], x[1]};
#pragma unroll
          for (int i = 2; i < 32; i++) asm("max.xorsign.abs.bf16x2 %0, %0, %1;\n" : "+r"(m[i & 1]) : "r"(x[i]));
          asm("max.xorsign.abs.bf16x2 %0, %0, %1;\n" : "+r"(m[0]) : "r"(m[1]));
          const uint32_t e = max(__reduce_max_sync(0xffffffffu, max((m[0] >> 7) & 255u, (m[0] >> 23) & 255u)), 5u);
          const uint32_t sc = (259u - e) * 0x00800080u;
#pragma unroll
          for (int i = 0; i < 8; i++) {
            uint32_t o[4];
#pragma unroll
            for (int j = 0; j < 4; j++) {
              const uint32_t v = bmul2(x[4 * i + j], sc);
              asm("cvt.rn.f16x2.f32 %0, %1, %2;\n" : "=r"(o[j]) : "f"(bf_hi(v)), "f"(i + j == 0 ? h0 * bf_hi(sc) : bf_lo(v)));
            }
            sts128((dst + (i & 3) * 1024) ^ ((i >> 2) << 6), o[0], o[1], o[2], o[3]);
            load(nsrc, i);
          }
          if (n & 1) {
            const int f = min(max((int)e + eh - 129, 0), 254);
            if (lane < 2)
              asm volatile("st.async.weak.shared::cluster.mbarrier::complete_tx::bytes.b32 [%0], %2, [%1];\n"
                           ::"r"(mapa(sb + OFF_SC + rank * 32 + c * 4, lane)), "r"(mapa(bars + 8 * BAR_LAND, lane)), "r"(f << 7) : "memory");
          }
          eh = e;
        }
        fence_async_smem();
        __syncwarp();
        if (lane == 0) mbar_arrive(bars + 8 * BAR_UH);
        PROF(32);
      }
      if (hw < 3) {
        const uint32_t rb = mapa(bars, lane & 1);
        const uint32_t epoch = ld_relaxed(g_flag_o + (2 * cta + hw - 1)) + 1;
        const bool own = hw - 1 == (rb2 & 1);
        nb_sync(NB_OREADY + hw - 1, 160);
        if (lane == 0) {
          asm volatile("cp.async.bulk.global.shared::cta.bulk_group [%0], [%1], %2;\n" ::"l"(g_o + (size_t)cta * 16384 + (hw - 1) * 8192),
                       "r"(sb + OFF_OP + (own ? 16384 : 0)), "r"(16384) : "memory");
          bulk_commit();
        }
        if (lane < 2) {
          mbar_arrive_cluster(rb + 8 * (BAR_EMPTY2 + 2));
          mbar_arrive_cluster(rb + 8 * (BAR_EMPTY2 + 3));
        }
        if (lane == 0) {
          bulk_wait0();
          if (own) mbar_expect_tx(bars + 8 * (BAR_FULL2 + 1), 16384);
          mbar_arrive_cluster(mapa(bars, own ? rank : rank ^ 1) + 8 * BAR_X);
          st_release(g_flag_o + (2 * cta + hw - 1), epoch);
          mbar_arrive(bars + 8 * BAR_REL);
        }
        __syncwarp();
        PROF(own ? 17 : 19);
      } else {
        if (MODE == 0) {
          mbar_wait_idle(bars + 8 * BAR_X, 0);
          if (elect_one())
            asm volatile("cp.async.bulk.shared::cluster.shared::cta.mbarrier::complete_tx::bytes [%0], [%1], %2, [%3];\n"
                         ::"r"(mapa(sb + OFF_OP, rank ^ 1)), "r"(sb + OFF_OP + 16384), "r"(16384),
                         "r"(mapa(bars + 8 * BAR_FULL2, rank ^ 1)) : "memory");
        }
        if (MODE == 0) {
          mbar_wait_idle(bars + 8 * BAR_DEAD, 0);
          if (elect_one()) {
            tma_load_3d(sb + g2_b(2), &tmWo, bars + 8 * (BAR_FULL2 + 2), 0, g2_k(hp, 2) * 64, cb2 * 2);
            tma_load_3d(sb + g2_b(3), &tmWo, bars + 8 * (BAR_FULL2 + 3), 0, g2_k(hp, 3) * 64, cb2 * 2);
          }
        }
        __syncwarp();
      }
    }
    if (!halo_cta && MODE != 2) {
      {
        const int c8 = (4 * (lr >> 1) + 2 * (lm & 1) + (lr & 1)) & 7;
        const bool own = (lr >> 2) == rank;
        const uint32_t ya = sb + (own ? y_slot(c8 & 1, c8 >> 1) : OFF_LAND + c8 * 2048);
        const uint32_t yx = ((lm >> 1) ^ lr) << 4;
        const int row = (lane >> 4) * 8 + ((lane >> 3) & 1) * 16 + ((lane >> 2) & 1);
        uint2* og = reinterpret_cast<uint2*>(p.out + (size_t)(rank * 1024 + row) * (2 * DM) + (chb & ~1) * 8 + (lane & 3) * 4);
        const uint32_t qa = sb + OFF_Q + (lane >> 4) * 512 + (lane & 15) * 8;
        mbar_wait(bars + 8 * BAR_Q, 0);
        mbar_wait_idle(bars + 8 * BAR_LAND, 0);
        PROF(33);
        const uint32_t t0 = clock();
        const uint4 s4 = lds128(sb + OFF_SC + (lane & 3) * 16);
        const uint32_t sc[2] = {s4.x | (s4.y << 16), s4.z | (s4.w << 16)};
        auto fin = [&](uint32_t q2, uint32_t y2, uint32_t s2) {
          float lo, hi;
          asm("{\n.reg .b16 l, h;\nmov.b32 {l, h}, %2;\ncvt.f32.f16 %0, l;\ncvt.f32.f16 %1, h;\n}\n" : "=f"(lo), "=f"(hi) : "r"(y2));
          return bmul2(q2, bmul2(pack_bf16(lo, hi), s2));
        };
#pragma unroll 1
        for (int j = hw ? hw - 1 : 15; j < (hw ? 15 : 16); j += 3) {
          uint32_t y[4][4];
          uint2 q[8];
          while (hw && (uint32_t)clock() - t0 < j * PACE) __nanosleep(40);
          const uint32_t qj = qa + j * 2048;
#pragma unroll
          for (int i = 0; i < 4; i++) ldsm4t(y[i], ya + j * 128 + (yx ^ (i << 5)));
#pragma unroll
          for (int i = 0; i < 8; i++) q[i] = lds64(qj + (i >> 2) * 1024 + (i & 3) * 128);
#pragma unroll
          for (int i = 0; i < 8; i++) {
            og[(size_t)(j * 64 + (i >> 2) * 32 + (i & 3) * 2) * (2 * DM / 4)] =
                make_uint2(fin(q[i].x, y[i >> 1][2 * (i & 1)], sc[0]), fin(q[i].y, y[i >> 1][2 * (i & 1) + 1], sc[1]));
            if (i < 7) asm volatile("nanosleep.u32 40;\n" ::: "memory");
          }
        }
      }
      PROF(22);
    }
    cluster_sync_all();
  } else {
    asm volatile("setmaxnreg.inc.sync.aligned.u32 %0;\n" :: "n"(REG_MATH));
    if (warp == 0) PROF2(26);
    const int wg = warp >> 2;
    const int wtid = tid & 127;
    const bool signaller = (wtid == 0) || (wtid == 32);
    const uint32_t rbars = mapa(bars, wtid >> 5 & 1);

    if (halo_cta) {
      const uint32_t epoch = ld_relaxed(g_flag_h + blockIdx.x) + 1;
      float acc0[64], acc1[64];
      int s = 0, ph = 0;
#pragma unroll 1
      for (int kb = 0; kb < 16; kb++) {
        mbar_wait(bars + 8 * (BAR_FULLB + s), ph);
        const uint32_t st = sb + s * STGH;
        const uint64_t da = mkdesc(st, 16, 1024, 1);
        const uint64_t db = mkdesc(st + 8192 + wg * 32768, 8192, 1024, 1);
        wg_fence();
#pragma unroll
        for (int kk = 0; kk < 4; kk++) {
          wgmma_n128(acc0, da + 2 * kk, db + 128 * kk, kb + kk);
          wgmma_n128(acc1, da + 2 * kk, db + 1024 + 128 * kk, kb + kk);
        }
        wg_commit();
        wg_wait<0>();
        if (wtid == 0) mbar_arrive(bars + 8 * (BAR_EMPTYB + s));
        if (++s == 3) { s = 0; ph ^= 1; }
      }
      fence_regs(acc0);
      fence_regs(acc1);
      if ((warp & 3) != 3) {
#pragma unroll
        for (int hh = 0; hh < 2; hh++) {
          uint4* dst = g_halo + ((hh * 4 + (warp & 3) + 1) * 16 + blockIdx.x * 4) * 128 + wg * 64 + lane;
#pragma unroll
          for (int j = 0; j < 4; j++) {
            const int o = 16 * j + 2 * hh;
            dst[(j >> 1) * 128 + (j & 1) * 32] =
                make_uint4(pack_bf16(acc0[o], acc0[o + 1]), pack_bf16(acc0[o + 4], acc0[o + 5]),
                           pack_bf16(acc0[o + 8], acc0[o + 9]), pack_bf16(acc0[o + 12], acc0[o + 13]));
            dst[(2 + (j >> 1)) * 128 + (j & 1) * 32] =
                make_uint4(pack_bf16(acc1[o], acc1[o + 1]), pack_bf16(acc1[o + 4], acc1[o + 5]),
                           pack_bf16(acc1[o + 8], acc1[o + 9]), pack_bf16(acc1[o + 12], acc1[o + 13]));
          }
        }
      }
      nb_sync(NB_G1DONE, 256);
      if (tid == 0) st_release(g_flag_h + blockIdx.x, epoch);
      PROF(36);
      cluster_sync_all();
      return;
    }

    float acc[64];
    auto g2_step = [&](int s, int kb) {
      const uint64_t da = mkdesc(sb + g2_a(s) + wg * 8192, 16, 1024, 1);
      const uint64_t db = mkdesc(sb + g2_b(s), 8192, 1024, 1);
      wg_fence();
      wgmma_n128(acc, da, db, kb);
      wgmma_n128(acc, da + 2, db + 128, 1);
      wgmma_n128(acc, da + 4, db + 256, 1);
      wgmma_n128(acc, da + 6, db + 384, 1);
      wg_commit();
    };

    if (MODE != 2) {
    uint32_t a1[2][4], tw[16], d1[32];
    const uint32_t tb = sb + OFF_T + wtid * 16;
    const uint64_t dx = mkdesc(sb + OFF_U + wg * 4096, OFF_H - OFF_U, 1024, 1);
    auto s1 = [&](int it) {
      hmma_n128t<0>(d1, a1[0], dx + it * 512);
      hmma_n128t<1>(d1, a1[1], dx + it * 512 + 128);
      wg_commit();
    };
    auto ldtw = [&](int i) {
      const uint4 v = lds128(tb + T_TW + i * 2048);
      tw[4 * i] = v.x; tw[4 * i + 1] = v.y; tw[4 * i + 2] = v.z; tw[4 * i + 3] = v.w;
    };
    {
      float acc0[96], acc1[96];
      int sa = 0, pha = 0, sbb = 0, phb = 0;
      asm volatile("cp.async.wait_group 0;\n" ::: "memory");
      fence_async_smem();
      nb_sync(NB_FIRST, 256);
      if (tid == 0) {
        mbar_arrive(bars + 8 * BAR_FULLA);
        mbar_arrive(bars + 8 * BAR_FULLB);
      }
      PROF(0 + wg);
#pragma unroll 1
      for (int kb = 0; kb < 30; kb++) {
        if (!(kb & 1)) mbar_wait(bars + 8 * (BAR_FULLA + sa), pha);
        mbar_wait(bars + 8 * (BAR_FULLB + sbb), phb);
        if (kb == 0) PROF2(0 + wg);
        if (kb == 4 && wg == 0) PROF2(28);
        if (kb == 8 && wg == 0) PROF2(29);
        if (kb == 16 && wg == 0) PROF2(30);
        const uint64_t da = mkdesc(sb + sa * STG1A + wg * 16384 + (kb & 1) * 64, 16, 1024, 1);
        const uint64_t db = mkdesc(sb + OFF_1B + sbb * STG1B, 4096, 1024, 1);
        wg_fence();
        wgmma_n192(acc0, da, db, kb);
        wgmma_n192(acc1, da + 512, db, kb);
        wgmma_n192(acc0, da + 2, db + 128, 1);
        wgmma_n192(acc1, da + 514, db + 128, 1);
        wg_commit();
        wg_wait<1>();
        if (kb > 0) {
          if (wtid == 64) mbar_arrive(bars + 8 * (BAR_EMPTYB + (sbb == 0 ? NS1B - 1 : sbb - 1)));
          if (!(kb & 1) && signaller) mbar_arrive_cluster(rbars + 8 * (BAR_EMPTYA + (sa == 0 ? NS1A - 1 : sa - 1)));
        }
        if (++sbb == NS1B) { sbb = 0; phb ^= 1; }
        if ((kb & 1) && ++sa == NS1A) { sa = 0; pha ^= 1; }
      }
      const int blk0 = wg * 8 + (warp & 3);
      const int lr = lane & 7, lm = lane >> 3;
      const bool le0 = 2 * (lane & 3) <= (lane >> 2), le1 = 2 * (lane & 3) + 1 <= (lane >> 2);
      const uint32_t maskLE = (le0 ? 0x0000FFFFu : 0u) | (le1 ? 0xFFFF0000u : 0u);
      uint32_t k0[2][2][4], k1[2][2][4], qa[2][2][8];
      float l[2][2][4];
      {
        static_assert(15 % NS1A == 0 && 30 % NS1B == 0, "slots of the last k blocks");
        mbar_wait(bars + 8 * BAR_FULLA, 1);
        mbar_wait(bars + 8 * BAR_FULLB, 0);
        mbar_wait(bars + 8 * (BAR_FULLB + 1), 0);
        const uint64_t da = mkdesc(sb + wg * 16384, 16, 1024, 1);
        const uint64_t db = mkdesc(sb + OFF_1B, 4096, 1024, 1);
        wg_fence();
#pragma unroll
        for (int i = 0; i < 4; i++) wgmma_n192(acc0, da + 2 * i, db + (i >> 1) * (STG1B >> 4) + (i & 1) * 128, 1);
        wg_commit();
        wg_wait<1>();
        if (wtid == 64) mbar_arrive(bars + 8 * (BAR_EMPTYB + NS1B - 1));
#pragma unroll
        for (int i = 0; i < 2; i++) wgmma_n192(acc1, da + 512 + 2 * i, db + (i >> 1) * (STG1B >> 4) + (i & 1) * 128, 1);
        wg_commit();
        wg_wait<1>();
        fence_regs(acc0);
        attn_stage(sb, blk0, lane, acc0, k1[0]);
#pragma unroll
        for (int i = 2; i < 4; i++) wgmma_n192(acc1, da + 512 + 2 * i, db + (i >> 1) * (STG1B >> 4) + (i & 1) * 128, 1);
        wg_commit();
        attn_pack(acc0, qa[0], k0[0]);
        wg_wait<0>();
        fence_regs(acc1);
      }
      if (wtid == 64) mbar_arrive(bars + 8 * BAR_EMPTYB);
      PROF(2 + wg);
      attn_stage(sb, blk0 + 4, lane, acc1, k1[1]);
      __syncwarp();
      if (lane == 0) mbar_arrive(bars + 8 * BAR_STG);
      mbar_wait(bars + 8 * BAR_U, 0);
      attn_pack(acc1, qa[1], k0[1]);
      attn_own(k0[0], k1[0], le0, le1, qa[0], l[0]);
      attn_own(k0[1], k1[1], le0, le1, qa[1], l[1]);
      static_assert(OFF_VP == 0, "halo V rows");
      const uint32_t vl0 = sb + OFF_VP - 1024 + blk0 * 2048 + (lm >> 1) * 1024 + lr * 128 + (((lm & 1) ^ lr) << 4);
      const uint32_t vl[4] = {vl0, vl0 ^ 64, vl0 ^ 32, vl0 ^ 96};
      const uint32_t obase = sb + OFF_OP + (wg == (rb2 & 1) ? 16384 : 0) + ((warp & 3) * 16 + lr) * 128 + ((lm ^ lr) << 4);
      mbar_wait(bars + 8 * BAR_STG, 0);
      {
        uint32_t km[4][4], va[8][4], vb[8][4], pp[8];
        float x[8][2];
#pragma unroll
        for (int n = 0; n < 4; n++) {
          const int blk = blk0 + 4 * (n >> 1);
          to_arr(km[n], lds128(sb + (blk == 0 ? -HALO : OFF_KH + (blk - 1) * 2048) + (n & 1) * 512 + lane * 16));
        }
#pragma unroll
        for (int n = 0; n < 8; n++) {
          const uint32_t o = ((n >> 1) & 1) * 8192 + (n >> 2) * 1024;
          ldsm4t(va[n], vl[n & 1] + o);
          ldsm4t(vb[n], vl[2 + (n & 1)] + o);
        }
        const bool first = blk0 == 0 && gidx == 0;
#pragma unroll
        for (int n = 0; n < 4; n++) {
          const uint32_t(&q)[8] = qa[n >> 1][n & 1];
          float sm[4];
          mma16816_z(sm, q[0], q[1], q[2], q[3], km[n][0], km[n][1]);
          mma16816(sm, q[4], q[5], q[6], q[7], km[n][2], km[n][3]);
          if (n < 2 && first) sm[0] = sm[1] = -1e9f / 0.17677669529663687f;
          x[n][0] = le0 ? l[n >> 1][n & 1][0] : sm[0];
          x[n][1] = le1 ? l[n >> 1][n & 1][1] : sm[1];
          x[4 + n][0] = l[n >> 1][n & 1][2];
          x[4 + n][1] = l[n >> 1][n & 1][3];
        }
        quad_softmax<8>(x, pp);
#pragma unroll
        for (int n = 7; n >= 0; n--)
          attn_pv((obase ^ ((n & 1) << 6)) + ((n >> 1) & 1) * 8192 + (n >> 2) * 1024, va[n], vb[n], pp[n], maskLE);
      }
      fence_async_smem();
      nb_arrive(NB_OREADY + wg, 160);
    }

    {
      const int w = warp & 3;
      uint32_t a4[8][4];
      uint32_t d4[16];
      PROF(34 + wg);
      const uint64_t dz = mkdesc(sb + OFF_U + wg * 4096, 1024, 128, 0);
      const uint64_t db2 = mkdesc(sb + OFF_T + T_B2, 128, 256, 0);
      mbar_wait(bars + 8 * BAR_T, 0);
      mbar_wait(bars + 8 * BAR_UH, 0);
      to_arr(a1[0], lds128(tb + T_A1));
      to_arr(a1[1], lds128(tb + T_A1 + 2048));
      wg_fence();
      s1(0);
      ldtw(0);
      ldtw(1);
      const uint32_t za = sb + (w < 2 ? OFF_U : OFF_H) + wg * 4096 + (w & 1) * 8192 + lane * 16;
      const uint32_t yl = (wtid ^ (4 * rank + wg)) * 16;
      const uint32_t yown = mapa(sb, rank) + yl, yrem = mapa(sb + OFF_LAND + wg * 2048, rank ^ 1) + yl;
      const uint32_t yb[2] = {mapa(bars + 8 * BAR_LAND, 0), mapa(bars + 8 * BAR_LAND, 1)};
      wg_wait<0>();
      fence_regs(d1);
      auto s4 = [&]() {
        wg_fence();
#pragma unroll
        for (int ks = 0; ks < 8; ks++) {
          const uint64_t d = dz + (ks & 1) * 128 + ((ks >> 1) & 1) * 512 + (ks >> 2) * ((OFF_H - OFF_U) >> 4);
          if (ks == 0) hmma_n64t<0>(d4, a4[ks], d);
          else hmma_n64t<1>(d4, a4[ks], d);
        }
        wg_commit();
      };
      auto e4 = [&](int pr) {
        fence_regs(d4);
        mbar_wait(bars + 8 * (pr == 0 ? BAR_LFREE : BAR_DEAD + 1), 0);
#pragma unroll
        for (int u = 0; u < 2; u++) {
          const int it = 2 * pr + u;
          const uint32_t o = (yown + y_slot(wg, it)) ^ (pr << 5), m = (yrem + it * 4096) ^ (pr << 5);
          st_async128(rank ? m : o, yb[0], d4[8 * u], d4[8 * u + 1], d4[8 * u + 2], d4[8 * u + 3]);
          st_async128(rank ? o : m, yb[1], d4[8 * u + 4], d4[8 * u + 5], d4[8 * u + 6], d4[8 * u + 7]);
        }
      };
      uint32_t a2[2][2][2][4], a3[2][2][4], d2[2][2][8], d3[2][8];
      auto s2a = [&]() {
        wg_fence();
#pragma unroll
        for (int c = 0; c < 4; c++) hmma_n32<0, 0>(d2[c & 1][c >> 1], a2[0][c & 1][c >> 1], db2 + (c >> 1) * 128);
      };
      auto s2b = [&]() {
        wg_fence();
#pragma unroll
        for (int c = 0; c < 4; c++) {
          hmma_n32<1, 0>(d2[c & 1][c >> 1], a2[1][c & 1][c >> 1], db2 + (c >> 1) * 128 + 64);
          if (c & 1) wg_commit();
        }
      };
      fft_e1<0>(d1, tw, a2[0]);
      s2a();
      fft_e1<1>(d1, tw, a2[1]);
      s2b();
      s1(1);
      ldtw(2);
      ldtw(3);
#pragma unroll
      for (int i = 0; i < 8; i++) to_arr(a4[i], lds128(tb + T_A4 + i * 2048));
#pragma unroll
      for (int it = 0; it < 4; it++) {
        if (it == 2) wg_wait<3>(); else if (it == 3) wg_wait<1>(); else wg_wait<2>();
        fence_regs(d2[0][0]);
        fence_regs(d2[1][0]);
        fft_e2<0, 0>(d2[0][0], d2[1][0], a3[0]);
        fft_e2<0, 1>(d2[0][0], d2[1][0], a3[1]);
        if (it == 2) wg_wait<2>(); else if (it == 3) wg_wait<0>(); else wg_wait<1>();
        fence_regs(d2[0][1]);
        fence_regs(d2[1][1]);
        fft_e2<1, 0>(d2[0][1], d2[1][1], a3[0]);
        fft_e2<1, 1>(d2[0][1], d2[1][1], a3[1]);
        wg_fence();
        hmma_n32<0, 0>(d3[0], a3[0][0], db2);
        hmma_n32<0, 0>(d3[1], a3[0][1], db2);
        hmma_n32<1, 0>(d3[0], a3[1][0], db2 + 64);
        hmma_n32<1, 0>(d3[1], a3[1][1], db2 + 64);
        wg_commit();
        if (it < 3) {
          wg_wait<1>();
          if (it == 2) {
            if (wtid == 64) mbar_arrive(bars + 8 * BAR_DEAD);
            e4(0);
          }
          fence_regs(d1);
          fft_e1<0>(d1, tw, a2[0]);
          s2a();
          wg_commit();
          wg_wait<1>();
        }
        if (it == 3) wg_wait<0>();
        if (it == 3 && wtid == 64) mbar_arrive(bars + 8 * (BAR_DEAD + 1));
        fence_regs(d3[0]);
        fence_regs(d3[1]);
        fft_e3(d3, tw, za + (it & 1) * 512);
        if (it < 3) {
          fft_e1<1>(d1, tw, a2[1]);
          s2b();
        }
        if (it & 1) {
          fence_async_smem();
          nb_sync(NB_WG + wg, 128);
          if (it == 1 && signaller) mbar_arrive_cluster(rbars + 8 * BAR_LFREE);
          s4();
        }
        if (it < 2) s1(it + 2);
        if (w == 0) PROF3(40 + 4 * wg + it);
      }
      if (MODE == 0) {
        mbar_wait(bars + 8 * BAR_FULL2, 0);
        g2_step(0, 0);
        wg_wait<1>();
      } else {
        wg_wait<0>();
      }
      if (signaller) mbar_arrive_cluster(rbars + 8 * (BAR_EMPTY2 + 4));
      e4(1);
      if (MODE == 0) {
        wg_wait<0>();
        if (signaller) mbar_arrive_cluster(rbars + 8 * BAR_EMPTY2);
      }
      PROF(6 + wg);
    }
    }

    if (MODE != 1) {
      int s = MODE == 0, ph = 0;
#pragma unroll 1
      for (int kb = s; kb < STAG; kb++) {
        mbar_wait(bars + 8 * (BAR_FULL2 + s), ph);
        if (kb == 1) PROF(8 + wg);
        if (warp == 4) PROF2(40 + kb);
        g2_step(s, kb);
        wg_wait<0>();
        if (kb < 16 - NS2 && signaller) mbar_arrive_cluster(rbars + 8 * (BAR_EMPTY2 + s));
        if (++s == NS2) { s = 0; ph ^= 1; }
      }
      {
        if (wg == 0) nb_sync(NB_LEAD, 256);
#pragma unroll
        for (int kb = STAG; kb < 16; kb++) {
          mbar_wait(bars + 8 * (BAR_FULL2 + kb % NS2), (kb / NS2) & 1);
          g2_step(kb % NS2, 1);
        }
        if (wg == 1) nb_arrive(NB_LEAD, 256);
      }
      wg_wait<0>();
      fence_regs(acc);
      PROF(10 + wg);
      const int lr = lane & 7, lm = lane >> 3;
      const uint32_t wbase = sb + warp * 2048;
      const uint32_t base = wbase + (lr + 8 * (lm & 1)) * 128;
#pragma unroll
      for (int j = 0; j < 16; j += 2) {
        const uint32_t a = base + (j >> 3) * 16384 + ((((j & 7) + (lm >> 1)) ^ lr) << 4);
        stsm4(a, pack_bf16(acc[4 * j], acc[4 * j + 1]), pack_bf16(acc[4 * j + 2], acc[4 * j + 3]),
              pack_bf16(acc[4 * j + 4], acc[4 * j + 5]), pack_bf16(acc[4 * j + 6], acc[4 * j + 7]));
      }
      __syncwarp();
      {
        const int rr = lane >> 4, ck = lane & 7, hf = (lane >> 3) & 1;
        uint4* og = reinterpret_cast<uint4*>(p.out + (size_t)(2 * ((rb2 & 7) * 128 + warp * 16 + rr) + (rb2 >> 3)) * (2 * DM) + DM + cb2 * 128 + hf * 64 + ck * 8);
        uint4 v[8];
#pragma unroll
        for (int i = 0; i < 8; i++) v[i] = lds128(wbase + hf * 16384 + (2 * i + rr) * 128 + ((ck ^ ((2 * i + rr) & 7)) << 4));
#pragma unroll
        for (int i = 0; i < 8; i++) og[(size_t)i * 4 * (2 * DM / 8)] = v[i];
      }
      PROF(12 + wg);
    }
    cluster_sync_all();
  }
}

typedef CUresult (*EncodeFn)(CUtensorMap*, CUtensorMapDataType, cuuint32_t, void*, const cuuint64_t*, const cuuint64_t*,
                             const cuuint32_t*, const cuuint32_t*, CUtensorMapInterleave, CUtensorMapSwizzle,
                             CUtensorMapL2promotion, CUtensorMapFloatOOBfill);

void make_map(EncodeFn enc, CUtensorMap* tm, const void* base, int rank, const cuuint64_t* dims, const cuuint64_t* strides,
              const cuuint32_t* box, CUtensorMapSwizzle swz) {
  cuuint32_t es[5] = {1, 1, 1, 1, 1};
  enc(tm, CU_TENSOR_MAP_DATA_TYPE_BFLOAT16, rank, const_cast<void*>(base), dims, strides, box, es,
      CU_TENSOR_MAP_INTERLEAVE_NONE, swz, CU_TENSOR_MAP_L2_PROMOTION_L2_256B, CU_TENSOR_MAP_FLOAT_OOB_FILL_NONE);
}

}

extern "C" void kernel_launch(void* const* d_in, const int* in_sizes, int n_in, void* d_out, int out_size) {
  static EncodeFn enc = nullptr;
  static bool coresident = true;
  if (!enc) {
    void* fn = nullptr;
    cudaDriverEntryPointQueryResult qr;
    cudaGetDriverEntryPoint("cuTensorMapEncodeTiled", &fn, cudaEnableDefault, &qr);
    enc = (EncodeFn)fn;
    cudaFuncSetAttribute(fused_kernel<0>, cudaFuncAttributeMaxDynamicSharedMemorySize, SMEM_BYTES);
    cudaFuncSetAttribute(fused_kernel<1>, cudaFuncAttributeMaxDynamicSharedMemorySize, SMEM_BYTES);
    cudaFuncSetAttribute(fused_kernel<2>, cudaFuncAttributeMaxDynamicSharedMemorySize, SMEM_BYTES);
    cudaLaunchConfig_t cfg = {};
    cfg.gridDim = dim3(NCTA);
    cfg.blockDim = dim3(NTHREADS);
    cfg.dynamicSmemBytes = SMEM_BYTES;
    cudaLaunchAttribute at;
    at.id = cudaLaunchAttributeClusterDimension;
    at.val.clusterDim.x = 2;
    at.val.clusterDim.y = 1;
    at.val.clusterDim.z = 1;
    cfg.attrs = &at;
    cfg.numAttrs = 1;
    int nclusters = 0;
    if (cudaOccupancyMaxActiveClusters(&nclusters, fused_kernel<0>, &cfg) == cudaSuccess) coresident = nclusters >= NCTA / 2;
    (void)cudaGetLastError();
  }
  CUtensorMap tmX, tmW, tmWo, tmQ, tmXh, tmWh;
  {
    cuuint64_t dims[3] = {1024, 2, 1024};
    cuuint64_t str[2] = {2048, 4096};
    cuuint32_t box[3] = {64, 1, 128};
    make_map(enc, &tmX, d_in[6], 3, dims, str, box, CU_TENSOR_MAP_SWIZZLE_128B);
  }
  {
    cuuint64_t dims[3] = {1024, 1024, 3};
    cuuint64_t str[2] = {6144, 2048};
    cuuint32_t box[3] = {64, 32, 3};
    make_map(enc, &tmW, d_in[7], 3, dims, str, box, CU_TENSOR_MAP_SWIZZLE_128B);
  }
  {
    cuuint64_t dims[3] = {64, 1024, 16};
    cuuint64_t str[2] = {2048, 128};
    cuuint32_t box[3] = {64, 64, 2};
    make_map(enc, &tmWo, d_in[8], 3, dims, str, box, CU_TENSOR_MAP_SWIZZLE_128B);
  }
  {
    cuuint64_t dims[5] = {1024, 2, 2, 8, 64};
    cuuint64_t str[4] = {2048, 16 * 2048, 2 * 2048, 32 * 2048};
    cuuint32_t box[5] = {16, 2, 2, 8, 4};
    make_map(enc, &tmQ, d_in[0], 5, dims, str, box, CU_TENSOR_MAP_SWIZZLE_NONE);
  }
  {
    cuuint64_t dims[4] = {1024, 256, 2, 4};
    cuuint64_t str[3] = {4096, 2048, 256 * 4096};
    cuuint32_t box[4] = {64, 8, 2, 4};
    make_map(enc, &tmXh, d_in[6], 4, dims, str, box, CU_TENSOR_MAP_SWIZZLE_128B);
  }
  {
    cuuint64_t dims[3] = {64, 1024, 48};
    cuuint64_t str[2] = {6144, 128};
    cuuint32_t box[3] = {64, 64, 4};
    make_map(enc, &tmWh, d_in[7], 3, dims, str, box, CU_TENSOR_MAP_SWIZZLE_128B);
  }
  Params p;
  p.q = (const __nv_bfloat16*)d_in[0];
  p.k = (const __nv_bfloat16*)d_in[1];
  p.v = (const __nv_bfloat16*)d_in[2];
  p.shift_k = (const __nv_bfloat16*)d_in[3];
  p.ssm_k = (const __nv_bfloat16*)d_in[4];
  p.ssm_D = (const __nv_bfloat16*)d_in[5];
  p.x = (const __nv_bfloat16*)d_in[6];
  p.w = (const __nv_bfloat16*)d_in[7];
  p.wo = (const __nv_bfloat16*)d_in[8];
  p.out = (__nv_bfloat16*)d_out;
  if (coresident) {
    fused_kernel<0><<<NCTA, NTHREADS, SMEM_BYTES>>>(p, tmX, tmW, tmWo, tmQ, tmXh, tmWh);
  } else {
    fused_kernel<0><<<4, NTHREADS, SMEM_BYTES>>>(p, tmX, tmW, tmWo, tmQ, tmXh, tmWh);
    fused_kernel<1><<<NCTA, NTHREADS, SMEM_BYTES>>>(p, tmX, tmW, tmWo, tmQ, tmXh, tmWh);
    fused_kernel<2><<<NCTA, NTHREADS, SMEM_BYTES>>>(p, tmX, tmW, tmWo, tmQ, tmXh, tmWh);
  }
}
```

```cpp
#include <cuda_runtime.h>
#include <cuda.h>
#include <cuda_bf16.h>
#include <stdint.h>

namespace {

constexpr int SEQ = 2048;
constexpr int DM = 1024;
constexpr int NCTA = 132;
constexpr int NTHREADS = 384;

constexpr int STG1A = 32768;
constexpr int NS1A = 3;
constexpr int STG1B = 12288;
constexpr int NS1B = 5;
constexpr int OFF_1B = NS1A * STG1A;
constexpr int STG2 = 32768;
constexpr int NS2 = 5;
constexpr int STGH = 73728;
constexpr int OFF_VP = 0;
constexpr int OFF_OP = 1 * STG2;
constexpr int OFF_Q = 2 * STG2;
constexpr int T_A4 = 0, T_TW = 16384, T_B2 = 24576, T_A1 = 28672, T_END = 32768;
constexpr int OFF_U = 163840;
constexpr int OFF_H = OFF_U + 32768;
constexpr int OFF_T = OFF_U - T_END;
constexpr int OFF_LAND = 4 * STG2;
constexpr int OFF_BAR = OFF_H + 32768;
constexpr int OFF_SC = OFF_BAR + 512;
constexpr int HALO = 2048;
constexpr int SMEM_BYTES = HALO + OFF_BAR + 1024;
static_assert(OFF_T + T_A1 == OFF_1B + NS1B * STG1B && OFF_T + T_TW == OFF_1B + 4 * STG1B && OFF_LAND == OFF_T + T_A4, "layout");
static_assert(3 * STGH <= OFF_BAR && SMEM_BYTES <= 232448, "smem");

constexpr int BAR_FULLA = 0;
constexpr int BAR_EMPTYA = 3;
constexpr int BAR_FULLB = 6;
constexpr int BAR_EMPTYB = 11;
constexpr int BAR_FULL2 = 16;
constexpr int BAR_EMPTY2 = 21;
constexpr int BAR_T = 26;
constexpr int BAR_UH = 27;
constexpr int BAR_LFREE = 28;
constexpr int BAR_LAND = 29;
constexpr int BAR_U = 30;
constexpr int BAR_Q = 31;
constexpr int BAR_STG = 32;
constexpr int BAR_DEAD = 33;
constexpr int BAR_X = 35;
constexpr int BAR_REL = 36;

constexpr int NB_G1DONE = 1;
constexpr int NB_OREADY = 2;
constexpr int NB_WG = 4;
constexpr int NB_HELP3 = 6;
constexpr int NB_FIRST = 7;
constexpr int NB_LEAD = 8;

constexpr int REG_MATH = 224, REG_HELP = 56;
constexpr int PF0 = 20;
constexpr uint32_t PACE = 390;
constexpr int STAG = 12;
constexpr int SPIN_LIMIT = 1 << 20;

__device__ __align__(1024) __nv_bfloat16 g_o[SEQ * DM];
__device__ __align__(128) uint32_t g_flag_o[256];
__device__ uint32_t g_flag_h[4];
__device__ uint4 g_halo[128 * 128];
__device__ __align__(128) const uint32_t g_tab[T_END / 4] = {
0x3c003c00,0x3bf13bff,0,0xafd6a648,0x3c003c00,0x3b993bce,0,0xb505b303,0x3c003c00,0x3af63b50,0,0xb7e3b67c,
0x3c003c00,0x3a0f3a8a,0,0xb93ab89b,0x3bc33bfe,0x3b773bfa,0xb3c6aa48,0xb5c2acb5,0x3a6d3b3b,0x389b3a4f,0xb8c4b6d7,0xba8ab8ec,
0x381d395f,0x26483505,0xbaddb9ed,0xbbffbb99,0x30b23564,0xb848b444,0xbbeabb88,0xbac2bbb6,0x3b0e3bf6,0x3a8a3bf1,0xb78bae46,0xb89bafd6,
0x34a53913,0xa6483732,0xbba8ba2f,0xbbffbb25,0xb78bae46,0xbac2b7e3,0xbb0ebbf6,0xb848baf6,0xbba8ba2f,0xbb50bbfa,0xb4a5b913,0x367cacb5,
0x39ed3bea,0x393a3be2,0xb95fb0b2,0xba0fb179,0xb56433c6,0xb8ec2648,0xbb88bbc3,0xba4fbbff,0xbbfeba6d,0xbb25bbce,0xaa48b8c4,0x3732b303,
0xb6d7badd,0x3444b67c,0x3b3b381d,0x3bb63b50,0x38723bd9,0x37323bce,0xbaa7b23e,0xbb25b303,0xbaa7b23e,0xbbb6b67c,0xb872bbd9,0xb444bb50,
0xb872bbd9,0xacb5ba8a,0x3aa7323e,0x3bfa389b,0x3aa7323e,0x3bf139cb,0x38723bd9,0xafd63984,0x35643bc3,0x33033bb6,0xbb88b3c6,0xbbceb444,
0xbbfeb8c4,0xbb77ba0f,0x2a48ba6d,0x35c2b93a,0x36d7b81d,0x3a8aafd6,0x3b3b3add,0x389b3bf1,0x395f3bea,0x26483b25,0xb9ed30b2,0xbbffb732,
0x2e463ba8,0xa6483b99,0xbbf6b4a5,0xbbffb505,0xba2fbb0e,0xb848bbb6,0x3913b78b,0x3ac2b444,0x3bf634a5,0x3b50393a,0x2e463ba8,0xb67c3a0f,
0xb913378b,0xbbe2afd6,0xba2fbb0e,0xb179bbf1,0xb0b23b88,0xb4443b77,0xbbeab564,0xbbb6b5c2,0xb3c6bbfe,0x2cb5bbe2,0x3bc3aa48,0x3bfa3179,
0x38c43b3b,0x2fd63bff,0xba6d36d7,0xbbf12648,0xbaddb95f,0xb505bbce,0x381db9ed,0x3b99b303,0xb61f3b64,0xb7e33b50,0xbb64b61f,0xbaf6b67c,
0x361fbb64,0x393aba8a,0x3b64361f,0x3a0f389b,0xb61f3b64,0xba4f3984,0xbb64b61f,0xb8ecb9cb,0x361fbb64,0x3b25b848,0x3b64361f,0x37323ac2,
0xb8c43b3b,0xb9843b25,0xba6db6d7,0xb9cbb732,0x3addb95f,0x3bceb7e3,0x381d39ed,0x33033af6,0xbbea3564,0xbb77acb5,0xb0b2bb88,0x35c2bbfa,
0x3bc32a48,0x389b38ec,0xb3c63bfe,0xba8a3a4f,0xba2f3b0e,0xbac23af6,0xb913b78b,0xb848b7e3,0x3bf6b4a5,0x3b50acb5,0xae463ba8,0xb67c3bfa,
0xb913b78b,0xb179ba4f,0x3a2fbb0e,0x3be2b8ec,0xae463ba8,0xb9cb3b99,0xbbf634a5,0xb984b505,0xbb3b3add,0xbb993ac2,0xb6d7b81d,0xb505b848,
0x39ed30b2,0x37e335c2,0xb95f3bea,0xbaf63b77,0x3564bbc3,0x3a0fbbe2,0x3b88b3c6,0x393a3179,0xbbfe38c4,0xba4f2648,0xaa48ba6d,0x38ecbbff,
0xbbd93aa7,0xbbfa3a8a,0xb23eb872,0xacb5b89b,0x323e3872,0xafd639cb,0xbbd93aa7,0xbbf13984,0x3bd9baa7,0x3b99b848,0x323e3872,0xb5053ac2,
0xb23eb872,0x37e3bb77,0x3bd9baa7,0x3af6b5c2,0xbbfe3a6d,0xbbe23a4f,0x2a48b8c4,0x3179b8ec,0xb6d73add,0xb9843b99,0xbb3b381d,0xb9cb3505,
0x395fb0b2,0x33033444,0xb9ed3bea,0xbbce3bb6,0x3b88bbc3,0x3b77b93a,0x356433c6,0xb5c23a0f,0xbba83a2f,0xbb503a0f,0x34a5b913,0x367cb93a,
0xbb0e3bf6,0xbbe23bf1,0xb78b2e46,0xb179afd6,0xb4a53913,0xb9cb3b25,0xbba83a2f,0xb9843732,0x378bae46,0xb30337e3,0xbb0e3bf6,0xbbce3af6,
0xbadd39ed,0xba4f39cb,0x381db95f,0x38ecb984,0xbbea3b88,0xbb253ac2,0x30b2b564,0x3732b848,0xbbc33bfe,0xbbb63b77,0xb3c62a48,0x3444b5c2,
0xba6d3b3b,0xbbfa3be2,0xb8c436d7,0x2cb5b179,0xb9a839a8,0xb8ec3984,0x39a8b9a8,0x3a4fb9cb,0xb9a839a8,0xb7323848,0x39a8b9a8,0x3b25bac2,
0xb9a839a8,0xb44435c2,0x39a8b9a8,0x3bb6bb77,0xb9a839a8,0xacb53179,0x39a8b9a8,0x3bfabbe2,0xb81d395f,0xb67c393a,0x3addb9ed,0x3b50ba0f,
0xb0b23564,0x31792fd6,0x3beabb88,0x3be2bbf1,0x33c6aa48,0x3984b732,0x3bc3bbfe,0x39cbbb25,0x38c4b6d7,0x3bcebaf6,0x3a6dbb3b,0x3303b7e3,
0xb4a53913,0xb17938ec,0x3ba8ba2f,0x3be2ba4f,0x378bae46,0x39cbb505,0x3b0ebbf6,0x3984bb99,0x3ba8ba2f,0x3bcebbb6,0x34a5b913,0xb303b444,
0x3b0ebbf6,0x35c2ba0f,0xb78b2e46,0xbb77393a,0xaa4838c4,0x2cb5389b,0x3bfeba6d,0x3bfaba8a,0x3b3bb81d,0x3bf1b984,0x36d7badd,0x2fd6b9cb,
0x39edbbea,0x3505bac2,0xb95f30b2,0xbb993848,0xb564b3c6,0xbaf635c2,0xbb883bc3,0xb7e33b77,0x323e3872,0x35053848,0x3bd9baa7,0x3b99bac2,
0x3bd9baa7,0x3af6bb77,0xb23eb872,0xb7e3b5c2,0xb23eb872,0xb93ab179,0xbbd93aa7,0xba0f3be2,0xbbd93aa7,0xb8ec3bff,0x323e3872,0x3a4fa648,
0x36d7381d,0x384837e3,0x3b3bbadd,0x3ac2baf6,0x395fbbea,0x367cbbfa,0xb9edb0b2,0xbb502cb5,0xbb8833c6,0xbbe238ec,0xb5643bc3,0x31793a4f,
0x2a483a6d,0x39843505,0x3bfeb8c4,0x39cbbb99,0x3913378b,0x39cb3732,0x3a2fbb0e,0x3984bb25,0x2e46bba8,0xb303baf6,0xbbf634a5,0xbbce37e3,
0xba2f3b0e,0xb5c23bfa,0x3913378b,0x3b772cb5,0x3bf6b4a5,0x3a8aba4f,0x2e46bba8,0xb89bb8ec,0x3a6d36d7,0x3af6367c,0x38c4bb3b,0x37e3bb50,
0xb81db9ed,0xba0fb89b,0xbadd395f,0xb93a3a8a,0x30b23b88,0x38ec39cb,0x3beab564,0x3a4fb984,0x33c6bbfe,0xb732bac2,0xbbc3aa48,0xbb253848,
0x3b64361f,0x3bb635c2,0x361fbb64,0x3444bb77,0xbb64b61f,0xbbfab179,0xb61f3b64,0xacb53be2,0x3b64361f,0x3bf1a648,0x361fbb64,0xafd6bbff,
0xbb64b61f,0xbb993303,0xb61f3b64,0x35053bce,0x3bea3564,0x3bff3505,0x30b2bb88,0x2648bb99,0xbbc32a48,0xbac23444,0x33c63bfe,0x38483bb6,
0x3a6db6d7,0x367cba0f,0xb8c4bb3b,0xbb50b93a,0xb81d39ed,0x31793bf1,0x3add395f,0x3be22fd6,0x3bf634a5,0x3bce3444,0xae46bba8,0xb303bbb6,
0xb913378b,0xb5c2393a,0x3a2f3b0e,0x3b773a0f,0xae46bba8,0xb89bbbf1,0xbbf6b4a5,0xba8a2fd6,0x3a2f3b0e,0x3bff3732,0x3913b78b,0xa648bb25,
0x3b8833c6,0x3b253303,0xb564bbc3,0xb732bbce,0xaa483a6d,0x34443b50,0x3bfe38c4,0x3bb6367c,0xbb3bbadd,0xbbfab89b,0xb6d7381d,0x2cb53a8a,
0x39edb0b2,0x2fd6b984,0xb95fbbea,0xbbf1b9cb,0x3aa7323e,0x3a0f3179,0xb872bbd9,0xb93abbe2,0x38723bd9,0x3a4f3bff,0x3aa7323e,0x38eca648,
0xbaa7b23e,0xb7323303,0x38723bd9,0x3b253bce,0xb872bbd9,0xbbb6bb50,0xbaa7b23e,0xb444367c,0x395f30b2,0x389b2fd6,0xb9edbbea,0xba8abbf1,
0x3b883bc3,0x3bff3b25,0x3564b3c6,0x2648b732,0x2a4838c4,0x38483af6,0x3bfe3a6d,0x3ac237e3,0xbb3bb81d,0xb67c2cb5,0x36d73add,0x3b503bfa,
0x378b2e46,0x35c22cb5,0xbb0ebbf6,0xbb77bbfa,0x3ba83a2f,0x3a8a38ec,0xb4a5b913,0xb89bba4f,0x3b0e3bf6,0x3bff3b99,0x378b2e46,0xa648b505,
0x34a53913,0x3ac23bb6,0x3ba83a2f,0x38483444,0x33c62a48,0x2fd62648,0xbbc3bbfe,0xbbf1bbff,0x38c436d7,0x35053303,0xba6dbb3b,0xbb99bbce,
0x3add39ed,0x37e3367c,0xb81db95f,0xbaf6bb50,0x3bea3b88,0x393a389b,0xb0b2b564,0xba0fba8a,0x3c003c00,0xbbf1bbff,0,0x2fd62648,
0x3c003c00,0xbb99bbce,0,0x35053303,0x3c003c00,0xbaf6bb50,0,0x37e3367c,0x3c003c00,0xba0fba8a,0,0x393a389b,
0x3bc33bfe,0xbb77bbfa,0xb3c6aa48,0x35c22cb5,0x3a6d3b3b,0xb89bba4f,0xb8c4b6d7,0x3a8a38ec,0x381d395f,0xa648b505,0xbaddb9ed,0x3bff3b99,
0x30b23564,0x38483444,0xbbeabb88,0x3ac23bb6,0x3b0e3bf6,0xba8abbf1,0xb78bae46,0x389b2fd6,0x34a53913,0x2648b732,0xbba8ba2f,0x3bff3b25,
0xb78bae46,0x3ac237e3,0xbb0ebbf6,0x38483af6,0xbba8ba2f,0x3b503bfa,0xb4a5b913,0xb67c2cb5,0x39ed3bea,0xb93abbe2,0xb95fb0b2,0x3a0f3179,
0xb56433c6,0x38eca648,0xbb88bbc3,0x3a4f3bff,0xbbfeba6d,0x3b253bce,0xaa48b8c4,0xb7323303,0xb6d7badd,0xb444367c,0x3b3b381d,0xbbb6bb50,
0x38723bd9,0xb732bbce,0xbaa7b23e,0x3b253303,0xbaa7b23e,0x3bb6367c,0xb872bbd9,0x34443b50,0xb872bbd9,0x2cb53a8a,0x3aa7323e,0xbbfab89b,
0x3aa7323e,0xbbf1b9cb,0x38723bd9,0x2fd6b984,0x35643bc3,0xb303bbb6,0xbb88b3c6,0x3bce3444,0xbbfeb8c4,0x3b773a0f,0x2a48ba6d,0xb5c2393a,
0x36d7b81d,0xba8a2fd6,0x3b3b3add,0xb89bbbf1,0x395f3bea,0xa648bb25,0xb9ed30b2,0x3bff3732,0x2e463ba8,0x2648bb99,0xbbf6b4a5,0x3bff3505,
0xba2fbb0e,0x38483bb6,0x3913b78b,0xbac23444,0x3bf634a5,0xbb50b93a,0x2e463ba8,0x367cba0f,0xb913378b,0x3be22fd6,0xba2fbb0e,0x31793bf1,
0xb0b23b88,0x3444bb77,0xbbeab564,0x3bb635c2,0xb3c6bbfe,0xacb53be2,0x3bc3aa48,0xbbfab179,0x38c43b3b,0xafd6bbff,0xba6d36d7,0x3bf1a648,
0xbaddb95f,0x35053bce,0x381db9ed,0xbb993303,0xb61f3b64,0x37e3bb50,0xbb64b61f,0x3af6367c,0x361fbb64,0xb93a3a8a,0x3b64361f,0xba0fb89b,
0xb61f3b64,0x3a4fb984,0xbb64b61f,0x38ec39cb,0x361fbb64,0xbb253848,0x3b64361f,0xb732bac2,0xb8c43b3b,0x3984bb25,0xba6db6d7,0x39cb3732,
0x3addb95f,0xbbce37e3,0x381d39ed,0xb303baf6,0xbbea3564,0x3b772cb5,0xb0b2bb88,0xb5c23bfa,0x3bc32a48,0xb89bb8ec,0xb3c63bfe,0x3a8aba4f,
0xba2f3b0e,0x3ac2baf6,0xb913b78b,0x384837e3,0x3bf6b4a5,0xbb502cb5,0xae463ba8,0x367cbbfa,0xb913b78b,0x31793a4f,0x3a2fbb0e,0xbbe238ec,
0xae463ba8,0x39cbbb99,0xbbf634a5,0x39843505,0xbb3b3add,0x3b99bac2,0xb6d7b81d,0x35053848,0x39ed30b2,0xb7e3b5c2,0xb95f3bea,0x3af6bb77,
0x3564bbc3,0xba0f3be2,0x3b88b3c6,0xb93ab179,0xbbfe38c4,0x3a4fa648,0xaa48ba6d,0xb8ec3bff,0xbbd93aa7,0x3bfaba8a,0xb23eb872,0x2cb5389b,
0x323e3872,0x2fd6b9cb,0xbbd93aa7,0x3bf1b984,0x3bd9baa7,0xbb993848,0x323e3872,0x3505bac2,0xb23eb872,0xb7e33b77,0x3bd9baa7,0xbaf635c2,
0xbbfe3a6d,0x3be2ba4f,0x2a48b8c4,0xb17938ec,0xb6d73add,0x3984bb99,0xbb3b381d,0x39cbb505,0x395fb0b2,0xb303b444,0xb9ed3bea,0x3bcebbb6,
0x3b88bbc3,0xbb77393a,0x356433c6,0x35c2ba0f,0xbba83a2f,0x3b50ba0f,0x34a5b913,0xb67c393a,0xbb0e3bf6,0x3be2bbf1,0xb78b2e46,0x31792fd6,
0xb4a53913,0x39cbbb25,0xbba83a2f,0x3984b732,0x378bae46,0x3303b7e3,0xbb0e3bf6,0x3bcebaf6,0xbadd39ed,0x3a4fb9cb,0x381db95f,0xb8ec3984,
0xbbea3b88,0x3b25bac2,0x30b2b564,0xb7323848,0xbbc33bfe,0x3bb6bb77,0xb3c62a48,0xb44435c2,0xba6d3b3b,0x3bfabbe2,0xb8c436d7,0xacb53179,
0xb9a839a8,0x38ecb984,0x39a8b9a8,0xba4f39cb,0xb9a839a8,0x3732b848,0x39a8b9a8,0xbb253ac2,0xb9a839a8,0x3444b5c2,0x39a8b9a8,0xbbb63b77,
0xb9a839a8,0x2cb5b179,0x39a8b9a8,0xbbfa3be2,0xb81d395f,0x367cb93a,0x3addb9ed,0xbb503a0f,0xb0b23564,0xb179afd6,0x3beabb88,0xbbe23bf1,
0x33c6aa48,0xb9843732,0x3bc3bbfe,0xb9cb3b25,0x38c4b6d7,0xbbce3af6,0x3a6dbb3b,0xb30337e3,0xb4a53913,0x3179b8ec,0x3ba8ba2f,0xbbe23a4f,
0x378bae46,0xb9cb3505,0x3b0ebbf6,0xb9843b99,0x3ba8ba2f,0xbbce3bb6,0x34a5b913,0x33033444,0x3b0ebbf6,0xb5c23a0f,0xb78b2e46,0x3b77b93a,
0xaa4838c4,0xacb5b89b,0x3bfeba6d,0xbbfa3a8a,0x3b3bb81d,0xbbf13984,0x36d7badd,0xafd639cb,0x39edbbea,0xb5053ac2,0xb95f30b2,0x3b99b848,
0xb564b3c6,0x3af6b5c2,0xbb883bc3,0x37e3bb77,0x323e3872,0xb505b848,0x3bd9baa7,0xbb993ac2,0x3bd9baa7,0xbaf63b77,0xb23eb872,0x37e335c2,
0xb23eb872,0x393a3179,0xbbd93aa7,0x3a0fbbe2,0xbbd93aa7,0x38ecbbff,0x323e3872,0xba4f2648,0x36d7381d,0xb848b7e3,0x3b3bbadd,0xbac23af6,
0x395fbbea,0xb67c3bfa,0xb9edb0b2,0x3b50acb5,0xbb8833c6,0x3be2b8ec,0xb5643bc3,0xb179ba4f,0x2a483a6d,0xb984b505,0x3bfeb8c4,0xb9cb3b99,
0x3913378b,0xb9cbb732,0x3a2fbb0e,0xb9843b25,0x2e46bba8,0x33033af6,0xbbf634a5,0x3bceb7e3,0xba2f3b0e,0x35c2bbfa,0x3913378b,0xbb77acb5,
0x3bf6b4a5,0xba8a3a4f,0x2e46bba8,0x389b38ec,0x3a6d36d7,0xbaf6b67c,0x38c4bb3b,0xb7e33b50,0xb81db9ed,0x3a0f389b,0xbadd395f,0x393aba8a,
0x30b23b88,0xb8ecb9cb,0x3beab564,0xba4f3984,0x33c6bbfe,0x37323ac2,0xbbc3aa48,0x3b25b848,0x3b64361f,0xbbb6b5c2,0x361fbb64,0xb4443b77,
0xbb64b61f,0x3bfa3179,0xb61f3b64,0x2cb5bbe2,0x3b64361f,0xbbf12648,0x361fbb64,0x2fd63bff,0xbb64b61f,0x3b99b303,0xb61f3b64,0xb505bbce,
0x3bea3564,0xbbffb505,0x30b2bb88,0xa6483b99,0xbbc32a48,0x3ac2b444,0x33c63bfe,0xb848bbb6,0x3a6db6d7,0xb67c3a0f,0xb8c4bb3b,0x3b50393a,
0xb81d39ed,0xb179bbf1,0x3add395f,0xbbe2afd6,0x3bf634a5,0xbbceb444,0xae46bba8,0x33033bb6,0xb913378b,0x35c2b93a,0x3a2f3b0e,0xbb77ba0f,
0xae46bba8,0x389b3bf1,0xbbf6b4a5,0x3a8aafd6,0x3a2f3b0e,0xbbffb732,0x3913b78b,0x26483b25,0x3b8833c6,0xbb25b303,0xb564bbc3,0x37323bce,
0xaa483a6d,0xb444bb50,0x3bfe38c4,0xbbb6b67c,0xbb3bbadd,0x3bfa389b,0xb6d7381d,0xacb5ba8a,0x39edb0b2,0xafd63984,0xb95fbbea,0x3bf139cb,
0x3aa7323e,0xba0fb179,0xb872bbd9,0x393a3be2,0x38723bd9,0xba4fbbff,0x3aa7323e,0xb8ec2648,0xbaa7b23e,0x3732b303,0x38723bd9,0xbb25bbce,
0xb872bbd9,0x3bb63b50,0xbaa7b23e,0x3444b67c,0x395f30b2,0xb89bafd6,0xb9edbbea,0x3a8a3bf1,0x3b883bc3,0xbbffbb25,0x3564b3c6,0xa6483732,
0x2a4838c4,0xb848baf6,0x3bfe3a6d,0xbac2b7e3,0xbb3bb81d,0x367cacb5,0x36d73add,0xbb50bbfa,0x378b2e46,0xb5c2acb5,0xbb0ebbf6,0x3b773bfa,
0x3ba83a2f,0xba8ab8ec,0xb4a5b913,0x389b3a4f,0x3b0e3bf6,0xbbffbb99,0x378b2e46,0x26483505,0x34a53913,0xbac2bbb6,0x3ba83a2f,0xb848b444,
0x33c62a48,0xafd6a648,0xbbc3bbfe,0x3bf13bff,0x38c436d7,0xb505b303,0xba6dbb3b,0x3b993bce,0x3add39ed,0xb7e3b67c,0xb81db95f,0x3af63b50,
0x3bea3b88,0xb93ab89b,0xb0b2b564,0x3a0f3a8a,0x3c003c00,0x38ec3984,0,0xba4fb9cb,0x3c003c00,0x37323848,0,0xbb25bac2,
0x3c003c00,0x344435c2,0,0xbbb6bb77,0x3c003c00,0x2cb53179,0,0xbbfabbe2,0xb3c6aa48,0xbb50ba0f,0xbbc3bbfe,0xb67cb93a,
0xb8c4b6d7,0xbbe2bbf1,0xba6dbb3b,0x3179afd6,0xbaddb9ed,0xb9cbbb25,0xb81db95f,0x39843732,0xbbeabb88,0xb303b7e3,0xb0b2b564,0x3bce3af6,
0xbb0ebbf6,0xb179b8ec,0x378b2e46,0x3be23a4f,0xb4a5b913,0x39cb3505,0x3ba83a2f,0x39843b99,0x378b2e46,0x3bce3bb6,0x3b0e3bf6,0xb3033444,
0x3ba83a2f,0x35c23a0f,0x34a53913,0xbb77b93a,0x395f30b2,0x3bfa3a8a,0x39ed3bea,0xacb5389b,0x3b883bc3,0x2fd639cb,0xb56433c6,0xbbf1b984,
0x2a4838c4,0xbb99b848,0xbbfeba6d,0xb505bac2,0xbb3bb81d,0xb7e3bb77,0xb6d7badd,0x3af635c2,0x38723bd9,0xb5053848,0xbaa7b23e,0xbb99bac2,
0xbaa7b23e,0xbaf6bb77,0xb872bbd9,0x37e3b5c2,0xb872bbd9,0x393ab179,0x3aa7323e,0x3a0f3be2,0x3aa7323e,0x38ec3bff,0x38723bd9,0xba4fa648,
0xbb88b3c6,0xbac2baf6,0xb564bbc3,0x3848b7e3,0x2a48ba6d,0x3b502cb5,0x3bfe38c4,0x367c3bfa,0x3b3b3add,0xb1793a4f,0xb6d7381d,0xbbe2b8ec,
0xb9ed30b2,0xb9cbbb99,0xb95fbbea,0x3984b505,0xae46bba8,0x39cbb732,0x3bf634a5,0x39843b25,0x3a2f3b0e,0xb3033af6,0xb913378b,0xbbceb7e3,
0xbbf6b4a5,0xb5c2bbfa,0xae46bba8,0x3b77acb5,0x3913b78b,0x3a8a3a4f,0x3a2f3b0e,0xb89b38ec,0x3bea3564,0x37e33b50,0xb0b23b88,0xbaf6367c,
0xbbc32a48,0xb93aba8a,0xb3c6bbfe,0x3a0fb89b,0x3a6db6d7,0x3a4f3984,0x38c43b3b,0xb8ec39cb,0xb81d39ed,0xbb25b848,0xbaddb95f,0x3732bac2,
0xb61f3b64,0xbbb635c2,0xbb64b61f,0xb444bb77,0x361fbb64,0x3bfab179,0x3b64361f,0x2cb53be2,0xb61f3b64,0xbbf1a648,0xbb64b61f,0x2fd6bbff,
0x361fbb64,0x3b993303,0x3b64361f,0xb5053bce,0xba6db6d7,0xa648bb99,0x38c4bb3b,0x3bffb505,0x381d39ed,0xb8483bb6,0xbadd395f,0xbac2b444,
0xb0b2bb88,0x3b50b93a,0x3beab564,0x367c3a0f,0xb3c63bfe,0xbbe22fd6,0xbbc3aa48,0x3179bbf1,0x3a2fbb0e,0x3bceb444,0x3913378b,0xb3033bb6,
0xbbf634a5,0xb5c2b93a,0x2e46bba8,0x3b77ba0f,0x3913378b,0xb89b3bf1,0xba2f3b0e,0xba8aafd6,0x2e46bba8,0x3bffb732,0x3bf6b4a5,0xa6483b25,
0x36d7381d,0xb7323bce,0xbb3b3add,0xbb253303,0x395fbbea,0x3bb6b67c,0x39ed30b2,0xb4443b50,0xbb8833c6,0x2cb5ba8a,0x3564bbc3,0x3bfab89b,
0x2a483a6d,0xbbf139cb,0xbbfe38c4,0xafd6b984,0xbbd93aa7,0xba0f3179,0xb23eb872,0x393abbe2,0x323e3872,0xba4f3bff,0xbbd93aa7,0xb8eca648,
0x3bd9baa7,0x37323303,0x323e3872,0xbb253bce,0xb23eb872,0x3bb6bb50,0x3bd9baa7,0x3444367c,0x2a48b8c4,0x3a8abbf1,0x3bfeba6d,0x389bafd6,
0xbb3b381d,0xa648b732,0x36d7badd,0x3bffbb25,0xb9ed3bea,0xbac237e3,0xb95f30b2,0x3848baf6,0x356433c6,0xbb503bfa,0xbb883bc3,0xb67cacb5,
0x3ba8ba2f,0x35c2acb5,0xb4a53913,0xbb773bfa,0x3b0ebbf6,0x3a8ab8ec,0x378bae46,0xb89b3a4f,0x34a5b913,0x3bffbb99,0x3ba8ba2f,0xa6483505,
0xb78b2e46,0x3ac2bbb6,0x3b0ebbf6,0x3848b444,0xb81d395f,0xbbf13bff,0xbadd39ed,0xafd62648,0xb0b23564,0xbb993bce,0xbbea3b88,0xb5053303,
0x33c6aa48,0xbaf63b50,0xbbc33bfe,0xb7e3367c,0x38c4b6d7,0xba0f3a8a,0xba6d3b3b,0xb93a389b,0xb9a839a8,0x2fd6a648,0x39a8b9a8,0x3bf1bbff,
0xb9a839a8,0x3505b303,0x39a8b9a8,0x3b99bbce,0xb9a839a8,0x37e3b67c,0x39a8b9a8,0x3af6bb50,0xb9a839a8,0x393ab89b,0x39a8b9a8,0x3a0fba8a,
0x3addb9ed,0x3b77bbfa,0x381db95f,0xb5c22cb5,0x3beabb88,0x389bba4f,0x30b2b564,0xba8a38ec,0x3bc3bbfe,0x2648b505,0xb3c62a48,0xbbff3b99,
0x3a6dbb3b,0xb8483444,0xb8c436d7,0xbac23bb6,0x34a5b913,0xb89b2fd6,0xbba83a2f,0xba8a3bf1,0xb78b2e46,0xbbff3b25,0xbb0e3bf6,0x26483732,
0xbba83a2f,0xb8483af6,0xb4a53913,0x3ac2b7e3,0xbb0e3bf6,0x367c2cb5,0x378bae46,0x3b50bbfa,0xbbfe3a6d,0xb93a3be2,0xaa4838c4,0x3a0fb179,
0xb6d73add,0x38ec2648,0x3b3bb81d,0x3a4fbbff,0x395fb0b2,0x3b25bbce,0x39edbbea,0xb732b303,0x3b88bbc3,0xb444b67c,0xb564b3c6,0xbbb63b50,
0x323e3872,0x3b25b303,0x3bd9baa7,0x3732bbce,0x3bd9baa7,0x3444bb50,0xb23eb872,0xbbb6367c,0xb23eb872,0xbbfa389b,0xbbd93aa7,0xacb53a8a,
0xbbd93aa7,0x2fd63984,0x323e3872,0x3bf1b9cb,0x3b3bbadd,0x3303bbb6,0xb6d7b81d,0xbbce3444,0xb9edb0b2,0xbb773a0f,0xb95f3bea,0x35c2393a,
0xb5643bc3,0x3a8a2fd6,0x3b88b3c6,0x389bbbf1,0x3bfeb8c4,0x2648bb25,0xaa48ba6d,0xbbff3732,0xb913b78b,0xbbff3505,0xba2f3b0e,0x26483b99,
0xae463ba8,0x3ac23444,0x3bf6b4a5,0x3848bbb6,0x3a2fbb0e,0xb67cba0f,0xb913b78b,0xbb50393a,0xbbf634a5,0xb1793bf1,0xae463ba8,0x3be2afd6,
0xb8c43b3b,0x34443b77,0x3a6d36d7,0x3bb6b5c2,0x3addb95f,0xacb5bbe2,0xb81db9ed,0xbbfa3179,0xbbea3564,0xafd63bff,0x30b23b88,0x3bf12648,
0x3bc32a48,0x3505bbce,0x33c6bbfe,0xbb99b303,0x3b64361f,0x3af6b67c,0x361fbb64,0xb7e3bb50,0xbb64b61f,0xba0f389b,0xb61f3b64,0x393a3a8a,
0x3b64361f,0x38ecb9cb,0x361fbb64,0xba4fb984,0xbb64b61f,0xb7323ac2,0xb61f3b64,0x3b253848,0x30b2bb88,0xb984bb25,0xbbeab564,0xb9cb3732,
0x33c63bfe,0x3bce37e3,0x3bc3aa48,0x3303baf6,0xb8c4bb3b,0xbb772cb5,0xba6d36d7,0x35c23bfa,0x3add395f,0x389bb8ec,0x381db9ed,0xba8aba4f,
0xbbf6b4a5,0xb84837e3,0x2e463ba8,0x3ac23af6,0x3913b78b,0xb67cbbfa,0xba2fbb0e,0xbb50acb5,0x2e463ba8,0x3be238ec,0x3bf634a5,0x3179ba4f,
0xba2fbb0e,0xb9843505,0xb913378b,0x39cb3b99,0x35643bc3,0x3b993ac2,0x3b8833c6,0x3505b848,0xbbfeb8c4,0xb7e335c2,0xaa483a6d,0x3af63b77,
0x36d7b81d,0xba0fbbe2,0xbb3bbadd,0xb93a3179,0x395f3bea,0x3a4f2648,0x39edb0b2,0xb8ecbbff,0x3aa7323e,0x2cb5b89b,0xb872bbd9,0xbbfaba8a,
0x38723bd9,0x3bf13984,0x3aa7323e,0xafd6b9cb,0xbaa7b23e,0x35053ac2,0x38723bd9,0x3b993848,0xb872bbd9,0xbaf6b5c2,0xbaa7b23e,0x37e33b77,
0xb9edbbea,0xbbe2ba4f,0xb95fb0b2,0x317938ec,0x3564b3c6,0xb984bb99,0xbb88bbc3,0xb9cbb505,0x3bfe3a6d,0x3303b444,0xaa48b8c4,0xbbcebbb6,
0x36d73add,0x3b77393a,0x3b3b381d,0xb5c2ba0f,0xb78bae46,0x367c393a,0x3b0e3bf6,0x3b503a0f,0xbba8ba2f,0xb1792fd6,0x34a53913,0x3be23bf1,
0xbb0ebbf6,0xb984b732,0xb78bae46,0x39cb3b25,0xb4a5b913,0xbbcebaf6,0xbba8ba2f,0x330337e3,0x3bc33bfe,0x3a4f39cb,0x33c62a48,0xb8ecb984,
0x3a6d3b3b,0x3b253ac2,0x38c436d7,0xb732b848,0x381d395f,0x3bb63b77,0x3add39ed,0xb444b5c2,0x30b23564,0x3bfa3be2,0x3bea3b88,0xacb5b179,
0x3c003c00,0xb8ecb984,0,0x3a4f39cb,0x3c003c00,0xb732b848,0,0x3b253ac2,0x3c003c00,0xb444b5c2,0,0x3bb63b77,
0x3c003c00,0xacb5b179,0,0x3bfa3be2,0xb3c6aa48,0x3b503a0f,0xbbc3bbfe,0x367c393a,0xb8c4b6d7,0x3be23bf1,0xba6dbb3b,0xb1792fd6,
0xbaddb9ed,0x39cb3b25,0xb81db95f,0xb984b732,0xbbeabb88,0x330337e3,0xb0b2b564,0xbbcebaf6,0xbb0ebbf6,0x317938ec,0x378b2e46,0xbbe2ba4f,
0xb4a5b913,0xb9cbb505,0x3ba83a2f,0xb984bb99,0x378b2e46,0xbbcebbb6,0x3b0e3bf6,0x3303b444,0x3ba83a2f,0xb5c2ba0f,0x34a53913,0x3b77393a,
0x395f30b2,0xbbfaba8a,0x39ed3bea,0x2cb5b89b,0x3b883bc3,0xafd6b9cb,0xb56433c6,0x3bf13984,0x2a4838c4,0x3b993848,0xbbfeba6d,0x35053ac2,
0xbb3bb81d,0x37e33b77,0xb6d7badd,0xbaf6b5c2,0x38723bd9,0x3505b848,0xbaa7b23e,0x3b993ac2,0xbaa7b23e,0x3af63b77,0xb872bbd9,0xb7e335c2,
0xb872bbd9,0xb93a3179,0x3aa7323e,0xba0fbbe2,0x3aa7323e,0xb8ecbbff,0x38723bd9,0x3a4f2648,0xbb88b3c6,0x3ac23af6,0xb564bbc3,0xb84837e3,
0x2a48ba6d,0xbb50acb5,0x3bfe38c4,0xb67cbbfa,0x3b3b3add,0x3179ba4f,0xb6d7381d,0x3be238ec,0xb9ed30b2,0x39cb3b99,0xb95fbbea,0xb9843505,
0xae46bba8,0xb9cb3732,0x3bf634a5,0xb984bb25,0x3a2f3b0e,0x3303baf6,0xb913378b,0x3bce37e3,0xbbf6b4a5,0x35c23bfa,0xae46bba8,0xbb772cb5,
0x3913b78b,0xba8aba4f,0x3a2f3b0e,0x389bb8ec,0x3bea3564,0xb7e3bb50,0xb0b23b88,0x3af6b67c,0xbbc32a48,0x393a3a8a,0xb3c6bbfe,0xba0f389b,
0x3a6db6d7,0xba4fb984,0x38c43b3b,0x38ecb9cb,0xb81d39ed,0x3b253848,0xbaddb95f,0xb7323ac2,0xb61f3b64,0x3bb6b5c2,0xbb64b61f,0x34443b77,
0x361fbb64,0xbbfa3179,0x3b64361f,0xacb5bbe2,0xb61f3b64,0x3bf12648,0xbb64b61f,0xafd63bff,0x361fbb64,0xbb99b303,0x3b64361f,0x3505bbce,
0xba6db6d7,0x26483b99,0x38c4bb3b,0xbbff3505,0x381d39ed,0x3848bbb6,0xbadd395f,0x3ac23444,0xb0b2bb88,0xbb50393a,0x3beab564,0xb67cba0f,
0xb3c63bfe,0x3be2afd6,0xbbc3aa48,0xb1793bf1,0x3a2fbb0e,0xbbce3444,0x3913378b,0x3303bbb6,0xbbf634a5,0x35c2393a,0x2e46bba8,0xbb773a0f,
0x3913378b,0x389bbbf1,0xba2f3b0e,0x3a8a2fd6,0x2e46bba8,0xbbff3732,0x3bf6b4a5,0x2648bb25,0x36d7381d,0x3732bbce,0xbb3b3add,0x3b25b303,
0x395fbbea,0xbbb6367c,0x39ed30b2,0x3444bb50,0xbb8833c6,0xacb53a8a,0x3564bbc3,0xbbfa389b,0x2a483a6d,0x3bf1b9cb,0xbbfe38c4,0x2fd63984,
0xbbd93aa7,0x3a0fb179,0xb23eb872,0xb93a3be2,0x323e3872,0x3a4fbbff,0xbbd93aa7,0x38ec2648,0x3bd9baa7,0xb732b303,0x323e3872,0x3b25bbce,
0xb23eb872,0xbbb63b50,0x3bd9baa7,0xb444b67c,0x2a48b8c4,0xba8a3bf1,0x3bfeba6d,0xb89b2fd6,0xbb3b381d,0x26483732,0x36d7badd,0xbbff3b25,
0xb9ed3bea,0x3ac2b7e3,0xb95f30b2,0xb8483af6,0x356433c6,0x3b50bbfa,0xbb883bc3,0x367c2cb5,0x3ba8ba2f,0xb5c22cb5,0xb4a53913,0x3b77bbfa,
0x3b0ebbf6,0xba8a38ec,0x378bae46,0x389bba4f,0x34a5b913,0xbbff3b99,0x3ba8ba2f,0x2648b505,0xb78b2e46,0xbac23bb6,0x3b0ebbf6,0xb8483444,
0xb81d395f,0x3bf1bbff,0xbadd39ed,0x2fd6a648,0xb0b23564,0x3b99bbce,0xbbea3b88,0x3505b303,0x33c6aa48,0x3af6bb50,0xbbc33bfe,0x37e3b67c,
0x38c4b6d7,0x3a0fba8a,0xba6d3b3b,0x393ab89b,0xb9a839a8,0xafd62648,0x39a8b9a8,0xbbf13bff,0xb9a839a8,0xb5053303,0x39a8b9a8,0xbb993bce,
0xb9a839a8,0xb7e3367c,0x39a8b9a8,0xbaf63b50,0xb9a839a8,0xb93a389b,0x39a8b9a8,0xba0f3a8a,0x3addb9ed,0xbb773bfa,0x381db95f,0x35c2acb5,
0x3beabb88,0xb89b3a4f,0x30b2b564,0x3a8ab8ec,0x3bc3bbfe,0xa6483505,0xb3c62a48,0x3bffbb99,0x3a6dbb3b,0x3848b444,0xb8c436d7,0x3ac2bbb6,
0x34a5b913,0x389bafd6,0xbba83a2f,0x3a8abbf1,0xb78b2e46,0x3bffbb25,0xbb0e3bf6,0xa648b732,0xbba83a2f,0x3848baf6,0xb4a53913,0xbac237e3,
0xbb0e3bf6,0xb67cacb5,0x378bae46,0xbb503bfa,0xbbfe3a6d,0x393abbe2,0xaa4838c4,0xba0f3179,0xb6d73add,0xb8eca648,0x3b3bb81d,0xba4f3bff,
0x395fb0b2,0xbb253bce,0x39edbbea,0x37323303,0x3b88bbc3,0x3444367c,0xb564b3c6,0x3bb6bb50,0x323e3872,0xbb253303,0x3bd9baa7,0xb7323bce,
0x3bd9baa7,0xb4443b50,0xb23eb872,0x3bb6b67c,0xb23eb872,0x3bfab89b,0xbbd93aa7,0x2cb5ba8a,0xbbd93aa7,0xafd6b984,0x323e3872,0xbbf139cb,
0x3b3bbadd,0xb3033bb6,0xb6d7b81d,0x3bceb444,0xb9edb0b2,0x3b77ba0f,0xb95f3bea,0xb5c2b93a,0xb5643bc3,0xba8aafd6,0x3b88b3c6,0xb89b3bf1,
0x3bfeb8c4,0xa6483b25,0xaa48ba6d,0x3bffb732,0xb913b78b,0x3bffb505,0xba2f3b0e,0xa648bb99,0xae463ba8,0xbac2b444,0x3bf6b4a5,0xb8483bb6,
0x3a2fbb0e,0x367c3a0f,0xb913b78b,0x3b50b93a,0xbbf634a5,0x3179bbf1,0xae463ba8,0xbbe22fd6,0xb8c43b3b,0xb444bb77,0x3a6d36d7,0xbbb635c2,
0x3addb95f,0x2cb53be2,0xb81db9ed,0x3bfab179,0xbbea3564,0x2fd6bbff,0x30b23b88,0xbbf1a648,0x3bc32a48,0xb5053bce,0x33c6bbfe,0x3b993303,
0x3b64361f,0xbaf6367c,0x361fbb64,0x37e33b50,0xbb64b61f,0x3a0fb89b,0xb61f3b64,0xb93aba8a,0x3b64361f,0xb8ec39cb,0x361fbb64,0x3a4f3984,
0xbb64b61f,0x3732bac2,0xb61f3b64,0xbb25b848,0x30b2bb88,0x39843b25,0xbbeab564,0x39cbb732,0x33c63bfe,0xbbceb7e3,0x3bc3aa48,0xb3033af6,
0xb8c4bb3b,0x3b77acb5,0xba6d36d7,0xb5c2bbfa,0x3add395f,0xb89b38ec,0x381db9ed,0x3a8a3a4f,0xbbf6b4a5,0x3848b7e3,0x2e463ba8,0xbac2baf6,
0x3913b78b,0x367c3bfa,0xba2fbb0e,0x3b502cb5,0x2e463ba8,0xbbe2b8ec,0x3bf634a5,0xb1793a4f,0xba2fbb0e,0x3984b505,0xb913378b,0xb9cbbb99,
0x35643bc3,0xbb99bac2,0x3b8833c6,0xb5053848,0xbbfeb8c4,0x37e3b5c2,0xaa483a6d,0xbaf6bb77,0x36d7b81d,0x3a0f3be2,0xbb3bbadd,0x393ab179,
0x395f3bea,0xba4fa648,0x39edb0b2,0x38ec3bff,0x3aa7323e,0xacb5389b,0xb872bbd9,0x3bfa3a8a,0x38723bd9,0xbbf1b984,0x3aa7323e,0x2fd639cb,
0xbaa7b23e,0xb505bac2,0x38723bd9,0xbb99b848,0xb872bbd9,0x3af635c2,0xbaa7b23e,0xb7e3bb77,0xb9edbbea,0x3be23a4f,0xb95fb0b2,0xb179b8ec,
0x3564b3c6,0x39843b99,0xbb88bbc3,0x39cb3505,0x3bfe3a6d,0xb3033444,0xaa48b8c4,0x3bce3bb6,0x36d73add,0xbb77b93a,0x3b3b381d,0x35c23a0f,
0xb78bae46,0xb67cb93a,0x3b0e3bf6,0xbb50ba0f,0xbba8ba2f,0x3179afd6,0x34a53913,0xbbe2bbf1,0xbb0ebbf6,0x39843732,0xb78bae46,0xb9cbbb25,
0xb4a5b913,0x3bce3af6,0xbba8ba2f,0xb303b7e3,0x3bc33bfe,0xba4fb9cb,0x33c62a48,0x38ec3984,0x3a6d3b3b,0xbb25bac2,0x38c436d7,0x37323848,
0x381d395f,0xbbb6bb77,0x3add39ed,0x344435c2,0x30b23564,0xbbfabbe2,0x3bea3b88,0x2cb53179,0x3c003c00,0xafd6a648,0,0xbbf1bbff,
0x3c003c00,0xb505b303,0,0xbb99bbce,0x3c003c00,0xb7e3b67c,0,0xbaf6bb50,0x3c003c00,0xb93ab89b,0,0xba0fba8a,
0xbbc3bbfe,0x35c22cb5,0x33c62a48,0x3b773bfa,0xba6dbb3b,0x3a8a38ec,0x38c436d7,0x389b3a4f,0xb81db95f,0x3bff3b99,0x3add39ed,0x26483505,
0xb0b2b564,0x3ac23bb6,0x3bea3b88,0xb848b444,0x3b0e3bf6,0xb89bafd6,0xb78bae46,0xba8abbf1,0x34a53913,0xbbffbb25,0xbba8ba2f,0x2648b732,
0xb78bae46,0xb848baf6,0xbb0ebbf6,0x3ac237e3,0xbba8ba2f,0x367cacb5,0xb4a5b913,0x3b503bfa,0xb9edbbea,0x3a0f3179,0x395f30b2,0x393a3be2,
0x3564b3c6,0x3a4f3bff,0x3b883bc3,0xb8ec2648,0x3bfe3a6d,0xb7323303,0x2a4838c4,0xbb25bbce,0x36d73add,0xbbb6bb50,0xbb3bb81d,0x3444b67c,
0x38723bd9,0xbb25b303,0xbaa7b23e,0xb732bbce,0xbaa7b23e,0xb444bb50,0xb872bbd9,0x3bb6367c,0xb872bbd9,0x3bfa389b,0x3aa7323e,0x2cb53a8a,
0x3aa7323e,0xafd63984,0x38723bd9,0xbbf1b9cb,0xb564bbc3,0x3bce3444,0x3b8833c6,0x33033bb6,0x3bfe38c4,0xb5c2393a,0xaa483a6d,0xbb77ba0f,
0xb6d7381d,0xb89bbbf1,0xbb3bbadd,0x3a8aafd6,0xb95fbbea,0x3bff3732,0x39edb0b2,0x26483b25,0x2e463ba8,0xbbffb505,0xbbf6b4a5,0x2648bb99,
0xba2fbb0e,0x3ac2b444,0x3913b78b,0x38483bb6,0x3bf634a5,0xb67c3a0f,0x2e463ba8,0xbb50b93a,0xb913378b,0xb179bbf1,0xba2fbb0e,0x3be22fd6,
0x30b2bb88,0x3bb635c2,0x3bea3564,0xb4443b77,0x33c63bfe,0xbbfab179,0xbbc32a48,0x2cb5bbe2,0xb8c4bb3b,0x3bf1a648,0x3a6db6d7,0x2fd63bff,
0x3add395f,0xbb993303,0xb81d39ed,0xb505bbce,0xb61f3b64,0xbaf6b67c,0xbb64b61f,0x37e3bb50,0x361fbb64,0x3a0f389b,0x3b64361f,0xb93a3a8a,
0xb61f3b64,0xb8ecb9cb,0xbb64b61f,0x3a4fb984,0x361fbb64,0x37323ac2,0x3b64361f,0xbb253848,0x38c4bb3b,0x39cb3732,0x3a6d36d7,0xb9843b25,
0xbadd395f,0xb303baf6,0xb81db9ed,0x3bceb7e3,0x3beab564,0xb5c23bfa,0x30b23b88,0xbb77acb5,0xbbc3aa48,0x3a8aba4f,0x33c6bbfe,0x389b38ec,
0xba2f3b0e,0xb848b7e3,0xb913b78b,0x3ac2baf6,0x3bf6b4a5,0xb67c3bfa,0xae463ba8,0xbb502cb5,0xb913b78b,0x3be2b8ec,0x3a2fbb0e,0x31793a4f,
0xae463ba8,0xb984b505,0xbbf634a5,0x39cbbb99,0x3b3bbadd,0x35053848,0x36d7381d,0xbb993ac2,0xb9edb0b2,0x3af6bb77,0x395fbbea,0x37e335c2,
0xb5643bc3,0xb93ab179,0xbb8833c6,0x3a0fbbe2,0x3bfeb8c4,0xb8ec3bff,0x2a483a6d,0xba4f2648,0xbbd93aa7,0xacb5b89b,0xb23eb872,0x3bfaba8a,
0x323e3872,0xbbf13984,0xbbd93aa7,0x2fd6b9cb,0x3bd9baa7,0xb5053ac2,0x323e3872,0xbb993848,0xb23eb872,0x3af6b5c2,0x3bd9baa7,0xb7e33b77,
0x3bfeba6d,0xb17938ec,0xaa4838c4,0xbbe23a4f,0x36d7badd,0x39cbb505,0x3b3bb81d,0xb9843b99,0xb95f30b2,0x3bcebbb6,0x39edbbea,0x33033444,
0xbb883bc3,0x35c2ba0f,0xb564b3c6,0x3b77b93a,0xbba83a2f,0x367cb93a,0x34a5b913,0x3b50ba0f,0xbb0e3bf6,0xb179afd6,0xb78b2e46,0x3be2bbf1,
0xb4a53913,0xb9843732,0xbba83a2f,0x39cbbb25,0x378bae46,0xbbce3af6,0xbb0e3bf6,0x3303b7e3,0x3addb9ed,0xb8ec3984,0xb81d395f,0xba4f39cb,
0x3beabb88,0xb7323848,0xb0b23564,0xbb253ac2,0x3bc3bbfe,0xb44435c2,0x33c6aa48,0xbbb63b77,0x3a6dbb3b,0xacb53179,0x38c4b6d7,0xbbfa3be2,
0xb9a839a8,0x3a4fb9cb,0x39a8b9a8,0x38ecb984,0xb9a839a8,0x3b25bac2,0x39a8b9a8,0x3732b848,0xb9a839a8,0x3bb6bb77,0x39a8b9a8,0x3444b5c2,
0xb9a839a8,0x3bfabbe2,0x39a8b9a8,0x2cb5b179,0x381db95f,0xbb503a0f,0xbadd39ed,0xb67c393a,0x30b2b564,0xbbe23bf1,0xbbea3b88,0x31792fd6,
0xb3c62a48,0xb9cb3b25,0xbbc33bfe,0x3984b732,0xb8c436d7,0xb30337e3,0xba6d3b3b,0x3bcebaf6,0xb4a53913,0x3be2ba4f,0x3ba8ba2f,0x3179b8ec,
0x378bae46,0x3984bb99,0x3b0ebbf6,0xb9cb3505,0x3ba8ba2f,0xb303b444,0x34a5b913,0xbbce3bb6,0x3b0ebbf6,0xbb77393a,0xb78b2e46,0xb5c23a0f,
0x2a48b8c4,0xbbfa3a8a,0xbbfe3a6d,0x2cb5389b,0xbb3b381d,0xafd639cb,0xb6d73add,0x3bf1b984,0xb9ed3bea,0x3b99b848,0x395fb0b2,0x3505bac2,
0x356433c6,0x37e3bb77,0x3b88bbc3,0xbaf635c2,0x323e3872,0x3b99bac2,0x3bd9baa7,0xb505b848,0x3bd9baa7,0xb7e3b5c2,0xb23eb872,0xbaf63b77,
0xb23eb872,0xba0f3be2,0xbbd93aa7,0x393a3179,0xbbd93aa7,0x3a4fa648,0x323e3872,0x38ecbbff,0xb6d7b81d,0xbac23af6,0xbb3b3add,0x384837e3,
0xb95f3bea,0x3b50acb5,0x39ed30b2,0x367cbbfa,0x3b88b3c6,0xb179ba4f,0x3564bbc3,0xbbe238ec,0xaa48ba6d,0xb9cb3b99,0xbbfe38c4,0x39843505,
0x3913378b,0x3984bb25,0x3a2fbb0e,0xb9cbb732,0x2e46bba8,0xbbce37e3,0xbbf634a5,0x33033af6,0xba2f3b0e,0x3b772cb5,0x3913378b,0x35c2bbfa,
0x3bf6b4a5,0xb89bb8ec,0x2e46bba8,0xba8a3a4f,0xba6db6d7,0xb7e33b50,0xb8c43b3b,0x3af6367c,0x381d39ed,0x393aba8a,0x3addb95f,0xba0fb89b,
0xb0b2bb88,0xba4f3984,0xbbea3564,0x38ec39cb,0xb3c63bfe,0x3b25b848,0x3bc32a48,0xb732bac2,0x3b64361f,0x3444bb77,0x361fbb64,0xbbb6b5c2,
0xbb64b61f,0xacb53be2,0xb61f3b64,0x3bfa3179,0x3b64361f,0xafd6bbff,0x361fbb64,0xbbf12648,0xbb64b61f,0x35053bce,0xb61f3b64,0x3b99b303,
0xbbeab564,0xa6483b99,0xb0b23b88,0x3bff3505,0x3bc3aa48,0xb848bbb6,0xb3c6bbfe,0xbac23444,0xba6d36d7,0x3b50393a,0x38c43b3b,0x367cba0f,
0x381db9ed,0xbbe2afd6,0xbaddb95f,0x31793bf1,0x3bf634a5,0xb303bbb6,0xae46bba8,0xbbceb444,0xb913378b,0x3b773a0f,0x3a2f3b0e,0x35c2b93a,
0xae46bba8,0xba8a2fd6,0xbbf6b4a5,0x389b3bf1,0x3a2f3b0e,0xa648bb25,0x3913b78b,0xbbffb732,0xbb88b3c6,0x37323bce,0x35643bc3,0x3b253303,
0x2a48ba6d,0xbbb6b67c,0xbbfeb8c4,0x34443b50,0x3b3b3add,0xacb5ba8a,0x36d7b81d,0xbbfab89b,0xb9ed30b2,0x3bf139cb,0x395f3bea,0x2fd6b984,
0x3aa7323e,0xb93abbe2,0xb872bbd9,0xba0fb179,0x38723bd9,0x38eca648,0x3aa7323e,0xba4fbbff,0xbaa7b23e,0x3b253bce,0x38723bd9,0x3732b303,
0xb872bbd9,0xb444367c,0xbaa7b23e,0x3bb63b50,0xb95fb0b2,0x3a8a3bf1,0x39ed3bea,0x389b2fd6,0xbb88bbc3,0xa6483732,0xb56433c6,0x3bff3b25,
0xaa48b8c4,0xbac2b7e3,0xbbfeba6d,0x38483af6,0x3b3b381d,0xbb50bbfa,0xb6d7badd,0xb67c2cb5,0x378b2e46,0xbb77bbfa,0xbb0ebbf6,0xb5c2acb5,
0x3ba83a2f,0xb89bba4f,0xb4a5b913,0xba8ab8ec,0x3b0e3bf6,0xa648b505,0x378b2e46,0xbbffbb99,0x34a53913,0x38483444,0x3ba83a2f,0xbac2bbb6,
0xb3c6aa48,0x3bf13bff,0x3bc33bfe,0x2fd62648,0xb8c4b6d7,0x3b993bce,0x3a6d3b3b,0x35053303,0xbaddb9ed,0x3af63b50,0x381d395f,0x37e3367c,
0xbbeabb88,0x3a0f3a8a,0x30b23564,0x393a389b,0x3c003c00,0x2fd62648,0,0x3bf13bff,0x3c003c00,0x35053303,0,0x3b993bce,
0x3c003c00,0x37e3367c,0,0x3af63b50,0x3c003c00,0x393a389b,0,0x3a0f3a8a,0xbbc3bbfe,0xb5c2acb5,0x33c62a48,0xbb77bbfa,
0xba6dbb3b,0xba8ab8ec,0x38c436d7,0xb89bba4f,0xb81db95f,0xbbffbb99,0x3add39ed,0xa648b505,0xb0b2b564,0xbac2bbb6,0x3bea3b88,0x38483444,
0x3b0e3bf6,0x389b2fd6,0xb78bae46,0x3a8a3bf1,0x34a53913,0x3bff3b25,0xbba8ba2f,0xa6483732,0xb78bae46,0x38483af6,0xbb0ebbf6,0xbac2b7e3,
0xbba8ba2f,0xb67c2cb5,0xb4a5b913,0xbb50bbfa,0xb9edbbea,0xba0fb179,0x395f30b2,0xb93abbe2,0x3564b3c6,0xba4fbbff,0x3b883bc3,0x38eca648,
0x3bfe3a6d,0x3732b303,0x2a4838c4,0x3b253bce,0x36d73add,0x3bb63b50,0xbb3bb81d,0xb444367c,0x38723bd9,0x3b253303,0xbaa7b23e,0x37323bce,
0xbaa7b23e,0x34443b50,0xb872bbd9,0xbbb6b67c,0xb872bbd9,0xbbfab89b,0x3aa7323e,0xacb5ba8a,0x3aa7323e,0x2fd6b984,0x38723bd9,0x3bf139cb,
0xb564bbc3,0xbbceb444,0x3b8833c6,0xb303bbb6,0x3bfe38c4,0x35c2b93a,0xaa483a6d,0x3b773a0f,0xb6d7381d,0x389b3bf1,0xbb3bbadd,0xba8a2fd6,
0xb95fbbea,0xbbffb732,0x39edb0b2,0xa648bb25,0x2e463ba8,0x3bff3505,0xbbf6b4a5,0xa6483b99,0xba2fbb0e,0xbac23444,0x3913b78b,0xb848bbb6,
0x3bf634a5,0x367cba0f,0x2e463ba8,0x3b50393a,0xb913378b,0x31793bf1,0xba2fbb0e,0xbbe2afd6,0x30b2bb88,0xbbb6b5c2,0x3bea3564,0x3444bb77,
0x33c63bfe,0x3bfa3179,0xbbc32a48,0xacb53be2,0xb8c4bb3b,0xbbf12648,0x3a6db6d7,0xafd6bbff,0x3add395f,0x3b99b303,0xb81d39ed,0x35053bce,
0xb61f3b64,0x3af6367c,0xbb64b61f,0xb7e33b50,0x361fbb64,0xba0fb89b,0x3b64361f,0x393aba8a,0xb61f3b64,0x38ec39cb,0xbb64b61f,0xba4f3984,
0x361fbb64,0xb732bac2,0x3b64361f,0x3b25b848,0x38c4bb3b,0xb9cbb732,0x3a6d36d7,0x3984bb25,0xbadd395f,0x33033af6,0xb81db9ed,0xbbce37e3,
0x3beab564,0x35c2bbfa,0x30b23b88,0x3b772cb5,0xbbc3aa48,0xba8a3a4f,0x33c6bbfe,0xb89bb8ec,0xba2f3b0e,0x384837e3,0xb913b78b,0xbac23af6,
0x3bf6b4a5,0x367cbbfa,0xae463ba8,0x3b50acb5,0xb913b78b,0xbbe238ec,0x3a2fbb0e,0xb179ba4f,0xae463ba8,0x39843505,0xbbf634a5,0xb9cb3b99,
0x3b3bbadd,0xb505b848,0x36d7381d,0x3b99bac2,0xb9edb0b2,0xbaf63b77,0x395fbbea,0xb7e3b5c2,0xb5643bc3,0x393a3179,0xbb8833c6,0xba0f3be2,
0x3bfeb8c4,0x38ecbbff,0x2a483a6d,0x3a4fa648,0xbbd93aa7,0x2cb5389b,0xb23eb872,0xbbfa3a8a,0x323e3872,0x3bf1b984,0xbbd93aa7,0xafd639cb,
0x3bd9baa7,0x3505bac2,0x323e3872,0x3b99b848,0xb23eb872,0xbaf635c2,0x3bd9baa7,0x37e3bb77,0x3bfeba6d,0x3179b8ec,0xaa4838c4,0x3be2ba4f,
0x36d7badd,0xb9cb3505,0x3b3bb81d,0x3984bb99,0xb95f30b2,0xbbce3bb6,0x39edbbea,0xb303b444,0xbb883bc3,0xb5c23a0f,0xb564b3c6,0xbb77393a,
0xbba83a2f,0xb67c393a,0x34a5b913,0xbb503a0f,0xbb0e3bf6,0x31792fd6,0xb78b2e46,0xbbe23bf1,0xb4a53913,0x3984b732,0xbba83a2f,0xb9cb3b25,
0x378bae46,0x3bcebaf6,0xbb0e3bf6,0xb30337e3,0x3addb9ed,0x38ecb984,0xb81d395f,0x3a4fb9cb,0x3beabb88,0x3732b848,0xb0b23564,0x3b25bac2,
0x3bc3bbfe,0x3444b5c2,0x33c6aa48,0x3bb6bb77,0x3a6dbb3b,0x2cb5b179,0x38c4b6d7,0x3bfabbe2,0xb9a839a8,0xba4f39cb,0x39a8b9a8,0xb8ec3984,
0xb9a839a8,0xbb253ac2,0x39a8b9a8,0xb7323848,0xb9a839a8,0xbbb63b77,0x39a8b9a8,0xb44435c2,0xb9a839a8,0xbbfa3be2,0x39a8b9a8,0xacb53179,
0x381db95f,0x3b50ba0f,0xbadd39ed,0x367cb93a,0x30b2b564,0x3be2bbf1,0xbbea3b88,0xb179afd6,0xb3c62a48,0x39cbbb25,0xbbc33bfe,0xb9843732,
0xb8c436d7,0x3303b7e3,0xba6d3b3b,0xbbce3af6,0xb4a53913,0xbbe23a4f,0x3ba8ba2f,0xb17938ec,0x378bae46,0xb9843b99,0x3b0ebbf6,0x39cbb505,
0x3ba8ba2f,0x33033444,0x34a5b913,0x3bcebbb6,0x3b0ebbf6,0x3b77b93a,0xb78b2e46,0x35c2ba0f,0x2a48b8c4,0x3bfaba8a,0xbbfe3a6d,0xacb5b89b,
0xbb3b381d,0x2fd6b9cb,0xb6d73add,0xbbf13984,0xb9ed3bea,0xbb993848,0x395fb0b2,0xb5053ac2,0x356433c6,0xb7e33b77,0x3b88bbc3,0x3af6b5c2,
0x323e3872,0xbb993ac2,0x3bd9baa7,0x35053848,0x3bd9baa7,0x37e335c2,0xb23eb872,0x3af6bb77,0xb23eb872,0x3a0fbbe2,0xbbd93aa7,0xb93ab179,
0xbbd93aa7,0xba4f2648,0x323e3872,0xb8ec3bff,0xb6d7b81d,0x3ac2baf6,0xbb3b3add,0xb848b7e3,0xb95f3bea,0xbb502cb5,0x39ed30b2,0xb67c3bfa,
0x3b88b3c6,0x31793a4f,0x3564bbc3,0x3be2b8ec,0xaa48ba6d,0x39cbbb99,0xbbfe38c4,0xb984b505,0x3913378b,0xb9843b25,0x3a2fbb0e,0x39cb3732,
0x2e46bba8,0x3bceb7e3,0xbbf634a5,0xb303baf6,0xba2f3b0e,0xbb77acb5,0x3913378b,0xb5c23bfa,0x3bf6b4a5,0x389b38ec,0x2e46bba8,0x3a8aba4f,
0xba6db6d7,0x37e3bb50,0xb8c43b3b,0xbaf6b67c,0x381d39ed,0xb93a3a8a,0x3addb95f,0x3a0f389b,0xb0b2bb88,0x3a4fb984,0xbbea3564,0xb8ecb9cb,
0xb3c63bfe,0xbb253848,0x3bc32a48,0x37323ac2,0x3b64361f,0xb4443b77,0x361fbb64,0x3bb635c2,0xbb64b61f,0x2cb5bbe2,0xb61f3b64,0xbbfab179,
0x3b64361f,0x2fd63bff,0x361fbb64,0x3bf1a648,0xbb64b61f,0xb505bbce,0xb61f3b64,0xbb993303,0xbbeab564,0x2648bb99,0xb0b23b88,0xbbffb505,
0x3bc3aa48,0x38483bb6,0xb3c6bbfe,0x3ac2b444,0xba6d36d7,0xbb50b93a,0x38c43b3b,0xb67c3a0f,0x381db9ed,0x3be22fd6,0xbaddb95f,0xb179bbf1,
0x3bf634a5,0x33033bb6,0xae46bba8,0x3bce3444,0xb913378b,0xbb77ba0f,0x3a2f3b0e,0xb5c2393a,0xae46bba8,0x3a8aafd6,0xbbf6b4a5,0xb89bbbf1,
0x3a2f3b0e,0x26483b25,0x3913b78b,0x3bff3732,0xbb88b3c6,0xb732bbce,0x35643bc3,0xbb25b303,0x2a48ba6d,0x3bb6367c,0xbbfeb8c4,0xb444bb50,
0x3b3b3add,0x2cb53a8a,0x36d7b81d,0x3bfa389b,0xb9ed30b2,0xbbf1b9cb,0x395f3bea,0xafd63984,0x3aa7323e,0x393a3be2,0xb872bbd9,0x3a0f3179,
0x38723bd9,0xb8ec2648,0x3aa7323e,0x3a4f3bff,0xbaa7b23e,0xbb25bbce,0x38723bd9,0xb7323303,0xb872bbd9,0x3444b67c,0xbaa7b23e,0xbbb6bb50,
0xb95fb0b2,0xba8abbf1,0x39ed3bea,0xb89bafd6,0xbb88bbc3,0x2648b732,0xb56433c6,0xbbffbb25,0xaa48b8c4,0x3ac237e3,0xbbfeba6d,0xb848baf6,
0x3b3b381d,0x3b503bfa,0xb6d7badd,0x367cacb5,0x378b2e46,0x3b773bfa,0xbb0ebbf6,0x35c22cb5,0x3ba83a2f,0x389b3a4f,0xb4a5b913,0x3a8a38ec,
0x3b0e3bf6,0x26483505,0x378b2e46,0x3bff3b99,0x34a53913,0xb848b444,0x3ba83a2f,0x3ac23bb6,0xb3c6aa48,0xbbf1bbff,0x3bc33bfe,0xafd6a648,
0xb8c4b6d7,0xbb99bbce,0x3a6d3b3b,0xb505b303,0xbaddb9ed,0xbaf6bb50,0x381d395f,0xb7e3b67c,0xbbeabb88,0xba0fba8a,0x30b23564,0xb93ab89b,
0x3c003c00,0xba4fb9cb,0,0xb8ecb984,0x3c003c00,0xbb25bac2,0,0xb732b848,0x3c003c00,0xbbb6bb77,0,0xb444b5c2,
0x3c003c00,0xbbfabbe2,0,0xacb5b179,0x33c62a48,0x367c393a,0x3bc33bfe,0xbb50ba0f,0x38c436d7,0xb1792fd6,0x3a6d3b3b,0xbbe2bbf1,
0x3add39ed,0xb984b732,0x381d395f,0xb9cbbb25,0x3bea3b88,0xbbcebaf6,0x30b23564,0xb303b7e3,0xbb0ebbf6,0x3be23a4f,0x378b2e46,0x317938ec,
0xb4a5b913,0x39843b99,0x3ba83a2f,0xb9cbb505,0x378b2e46,0xb3033444,0x3b0e3bf6,0xbbcebbb6,0x3ba83a2f,0xbb77b93a,0x34a53913,0xb5c2ba0f,
0xb95fb0b2,0x2cb5b89b,0xb9edbbea,0x3bfa3a8a,0xbb88bbc3,0x3bf13984,0x3564b3c6,0x2fd639cb,0xaa48b8c4,0x35053ac2,0x3bfe3a6d,0xbb99b848,
0x3b3b381d,0xbaf6b5c2,0x36d73add,0xb7e3bb77,0x38723bd9,0xbb99bac2,0xbaa7b23e,0x3505b848,0xbaa7b23e,0x37e3b5c2,0xb872bbd9,0x3af63b77,
0xb872bbd9,0x3a0f3be2,0x3aa7323e,0xb93a3179,0x3aa7323e,0xba4fa648,0x38723bd9,0xb8ecbbff,0x3b8833c6,0xb84837e3,0x35643bc3,0xbac2baf6,
0xaa483a6d,0xb67cbbfa,0xbbfeb8c4,0x3b502cb5,0xbb3bbadd,0x3be238ec,0x36d7b81d,0xb1793a4f,0x39edb0b2,0xb9843505,0x395f3bea,0xb9cbbb99,
0xae46bba8,0x39843b25,0x3bf634a5,0xb9cb3732,0x3a2f3b0e,0xbbceb7e3,0xb913378b,0x3303baf6,0xbbf6b4a5,0x3b77acb5,0xae46bba8,0x35c23bfa,
0x3913b78b,0xb89b38ec,0x3a2f3b0e,0xba8aba4f,0xbbeab564,0x3af6b67c,0x30b2bb88,0x37e33b50,0x3bc3aa48,0xba0f389b,0x33c63bfe,0xb93aba8a,
0xba6d36d7,0x38ecb9cb,0xb8c4bb3b,0x3a4f3984,0x381db9ed,0xb7323ac2,0x3add395f,0xbb25b848,0xb61f3b64,0xb444bb77,0xbb64b61f,0x3bb6b5c2,
0x361fbb64,0x2cb53be2,0x3b64361f,0xbbfa3179,0xb61f3b64,0x2fd6bbff,0xbb64b61f,0x3bf12648,0x361fbb64,0xb5053bce,0x3b64361f,0xbb99b303,
0x3a6d36d7,0xbbff3505,0xb8c43b3b,0xa648bb99,0xb81db9ed,0x3ac23444,0x3addb95f,0xb8483bb6,0x30b23b88,0xb67cba0f,0xbbea3564,0x3b50b93a,
0x33c6bbfe,0xb1793bf1,0x3bc32a48,0xbbe22fd6,0x3a2fbb0e,0xb3033bb6,0x3913378b,0xbbce3444,0xbbf634a5,0x3b77ba0f,0x2e46bba8,0x35c2393a,
0x3913378b,0xba8aafd6,0xba2f3b0e,0x389bbbf1,0x2e46bba8,0xa6483b25,0x3bf6b4a5,0xbbff3732,0xb6d7b81d,0x3b25b303,0x3b3bbadd,0xb7323bce,
0xb95f3bea,0x3444bb50,0xb9edb0b2,0x3bb6b67c,0x3b88b3c6,0xbbfa389b,0xb5643bc3,0x2cb5ba8a,0xaa48ba6d,0x2fd63984,0x3bfeb8c4,0xbbf139cb,
0xbbd93aa7,0x393abbe2,0xb23eb872,0x3a0fb179,0x323e3872,0xb8eca648,0xbbd93aa7,0x3a4fbbff,0x3bd9baa7,0xbb253bce,0x323e3872,0xb732b303,
0xb23eb872,0x3444367c,0x3bd9baa7,0xbbb63b50,0xaa4838c4,0xb89b2fd6,0xbbfe3a6d,0x3a8abbf1,0x3b3bb81d,0xbbff3b25,0xb6d73add,0xa648b732,
0x39edbbea,0xb8483af6,0x395fb0b2,0xbac237e3,0xb564b3c6,0x367c2cb5,0x3b88bbc3,0xbb503bfa,0x3ba8ba2f,0xbb773bfa,0xb4a53913,0xb5c22cb5,
0x3b0ebbf6,0xb89b3a4f,0x378bae46,0xba8a38ec,0x34a5b913,0xa6483505,0x3ba8ba2f,0xbbff3b99,0xb78b2e46,0x3848b444,0x3b0ebbf6,0xbac23bb6,
0x381db95f,0x2fd6a648,0x3addb9ed,0xbbf13bff,0x30b2b564,0x3505b303,0x3beabb88,0xbb993bce,0xb3c62a48,0x37e3b67c,0x3bc3bbfe,0xbaf63b50,
0xb8c436d7,0x393ab89b,0x3a6dbb3b,0xba0f3a8a,0xb9a839a8,0x3bf1bbff,0x39a8b9a8,0xafd62648,0xb9a839a8,0x3b99bbce,0x39a8b9a8,0xb5053303,
0xb9a839a8,0x3af6bb50,0x39a8b9a8,0xb7e3367c,0xb9a839a8,0x3a0fba8a,0x39a8b9a8,0xb93a389b,0xbadd39ed,0x35c2acb5,0xb81d395f,0x3b77bbfa,
0xbbea3b88,0x3a8ab8ec,0xb0b23564,0x389bba4f,0xbbc33bfe,0x3bffbb99,0x33c6aa48,0x2648b505,0xba6d3b3b,0x3ac2bbb6,0x38c4b6d7,0xb8483444,
0x34a5b913,0xba8a3bf1,0xbba83a2f,0x389bafd6,0xb78b2e46,0x26483732,0xbb0e3bf6,0x3bffbb25,0xbba83a2f,0x3ac2b7e3,0xb4a53913,0x3848baf6,
0xbb0e3bf6,0x3b50bbfa,0x378bae46,0xb67cacb5,0x3bfeba6d,0xba0f3179,0x2a48b8c4,0xb93a3be2,0x36d7badd,0xba4f3bff,0xbb3b381d,0x38ec2648,
0xb95f30b2,0x37323303,0xb9ed3bea,0x3b25bbce,0xbb883bc3,0x3bb6bb50,0x356433c6,0xb444b67c,0x323e3872,0x3732bbce,0x3bd9baa7,0xbb253303,
0x3bd9baa7,0xbbb6367c,0xb23eb872,0xb4443b50,0xb23eb872,0xacb53a8a,0xbbd93aa7,0x3bfab89b,0xbbd93aa7,0x3bf1b9cb,0x323e3872,0xafd6b984,
0xbb3b3add,0x3bceb444,0x36d7381d,0x3303bbb6,0x39ed30b2,0xb5c2b93a,0x395fbbea,0xbb773a0f,0x3564bbc3,0xb89b3bf1,0xbb8833c6,0x3a8a2fd6,
0xbbfe38c4,0x3bffb732,0x2a483a6d,0x2648bb25,0xb913b78b,0x26483b99,0xba2f3b0e,0x3bffb505,0xae463ba8,0x3848bbb6,0x3bf6b4a5,0xbac2b444,
0x3a2fbb0e,0xbb50393a,0xb913b78b,0x367c3a0f,0xbbf634a5,0x3be2afd6,0xae463ba8,0x3179bbf1,0x38c4bb3b,0xbbb635c2,0xba6db6d7,0x34443b77,
0xbadd395f,0x3bfab179,0x381d39ed,0xacb5bbe2,0x3beab564,0xbbf1a648,0xb0b2bb88,0xafd63bff,0xbbc3aa48,0x3b993303,0xb3c63bfe,0x3505bbce,
0x3b64361f,0xb7e3bb50,0x361fbb64,0xbaf6367c,0xbb64b61f,0x393a3a8a,0xb61f3b64,0x3a0fb89b,0x3b64361f,0xba4fb984,0x361fbb64,0xb8ec39cb,
0xbb64b61f,0x3b253848,0xb61f3b64,0x3732bac2,0xb0b23b88,0x39cbb732,0x3bea3564,0xb984bb25,0xb3c6bbfe,0xb3033af6,0xbbc32a48,0x3bce37e3,
0x38c43b3b,0xb5c2bbfa,0x3a6db6d7,0xbb772cb5,0xbaddb95f,0x3a8a3a4f,0xb81d39ed,0x389bb8ec,0xbbf6b4a5,0x3ac23af6,0x2e463ba8,0x3848b7e3,
0x3913b78b,0xbb50acb5,0xba2fbb0e,0x367c3bfa,0x2e463ba8,0x3179ba4f,0x3bf634a5,0xbbe2b8ec,0xba2fbb0e,0x39cb3b99,0xb913378b,0x3984b505,
0xb564bbc3,0xb5053848,0xbb88b3c6,0x3b993ac2,0x3bfe38c4,0xbaf6bb77,0x2a48ba6d,0xb7e335c2,0xb6d7381d,0x393ab179,0x3b3b3add,0xba0fbbe2,
0xb95fbbea,0x38ec3bff,0xb9ed30b2,0x3a4f2648,0x3aa7323e,0xbbfaba8a,0xb872bbd9,0xacb5389b,0x38723bd9,0xafd6b9cb,0x3aa7323e,0xbbf1b984,
0xbaa7b23e,0x3b993848,0x38723bd9,0xb505bac2,0xb872bbd9,0x37e33b77,0xbaa7b23e,0x3af635c2,0x39ed3bea,0xb179b8ec,0x395f30b2,0xbbe2ba4f,
0xb56433c6,0x39cb3505,0x3b883bc3,0xb984bb99,0xbbfeba6d,0x3bce3bb6,0x2a4838c4,0x3303b444,0xb6d7badd,0x35c23a0f,0xbb3bb81d,0x3b77393a,
0xb78bae46,0x3b503a0f,0x3b0e3bf6,0xb67cb93a,0xbba8ba2f,0x3be23bf1,0x34a53913,0x3179afd6,0xbb0ebbf6,0x39cb3b25,0xb78bae46,0x39843732,
0xb4a5b913,0x330337e3,0xbba8ba2f,0x3bce3af6,0xbbc3bbfe,0x38ec3984,0xb3c6aa48,0x3a4f39cb,0xba6dbb3b,0x37323848,0xb8c4b6d7,0x3b253ac2,
0xb81db95f,0x344435c2,0xbaddb9ed,0x3bb63b77,0xb0b2b564,0x2cb53179,0xbbeabb88,0x3bfa3be2,0x3c003c00,0x3a4f39cb,0,0x38ec3984,
0x3c003c00,0x3b253ac2,0,0x37323848,0x3c003c00,0x3bb63b77,0,0x344435c2,0x3c003c00,0x3bfa3be2,0,0x2cb53179,
0x33c62a48,0xb67cb93a,0x3bc33bfe,0x3b503a0f,0x38c436d7,0x3179afd6,0x3a6d3b3b,0x3be23bf1,0x3add39ed,0x39843732,0x381d395f,0x39cb3b25,
0x3bea3b88,0x3bce3af6,0x30b23564,0x330337e3,0xbb0ebbf6,0xbbe2ba4f,0x378b2e46,0xb179b8ec,0xb4a5b913,0xb984bb99,0x3ba83a2f,0x39cb3505,
0x378b2e46,0x3303b444,0x3b0e3bf6,0x3bce3bb6,0x3ba83a2f,0x3b77393a,0x34a53913,0x35c23a0f,0xb95fb0b2,0xacb5389b,0xb9edbbea,0xbbfaba8a,
0xbb88bbc3,0xbbf1b984,0x3564b3c6,0xafd6b9cb,0xaa48b8c4,0xb505bac2,0x3bfe3a6d,0x3b993848,0x3b3b381d,0x3af635c2,0x36d73add,0x37e33b77,
0x38723bd9,0x3b993ac2,0xbaa7b23e,0xb5053848,0xbaa7b23e,0xb7e335c2,0xb872bbd9,0xbaf6bb77,0xb872bbd9,0xba0fbbe2,0x3aa7323e,0x393ab179,
0x3aa7323e,0x3a4f2648,0x38723bd9,0x38ec3bff,0x3b8833c6,0x3848b7e3,0x35643bc3,0x3ac23af6,0xaa483a6d,0x367c3bfa,0xbbfeb8c4,0xbb50acb5,
0xbb3bbadd,0xbbe2b8ec,0x36d7b81d,0x3179ba4f,0x39edb0b2,0x3984b505,0x395f3bea,0x39cb3b99,0xae46bba8,0xb984bb25,0x3bf634a5,0x39cbb732,
0x3a2f3b0e,0x3bce37e3,0xb913378b,0xb3033af6,0xbbf6b4a5,0xbb772cb5,0xae46bba8,0xb5c2bbfa,0x3913b78b,0x389bb8ec,0x3a2f3b0e,0x3a8a3a4f,
0xbbeab564,0xbaf6367c,0x30b2bb88,0xb7e3bb50,0x3bc3aa48,0x3a0fb89b,0x33c63bfe,0x393a3a8a,0xba6d36d7,0xb8ec39cb,0xb8c4bb3b,0xba4fb984,
0x381db9ed,0x3732bac2,0x3add395f,0x3b253848,0xb61f3b64,0x34443b77,0xbb64b61f,0xbbb635c2,0x361fbb64,0xacb5bbe2,0x3b64361f,0x3bfab179,
0xb61f3b64,0xafd63bff,0xbb64b61f,0xbbf1a648,0x361fbb64,0x3505bbce,0x3b64361f,0x3b993303,0x3a6d36d7,0x3bffb505,0xb8c43b3b,0x26483b99,
0xb81db9ed,0xbac2b444,0x3addb95f,0x3848bbb6,0x30b23b88,0x367c3a0f,0xbbea3564,0xbb50393a,0x33c6bbfe,0x3179bbf1,0x3bc32a48,0x3be2afd6,
0x3a2fbb0e,0x3303bbb6,0x3913378b,0x3bceb444,0xbbf634a5,0xbb773a0f,0x2e46bba8,0xb5c2b93a,0x3913378b,0x3a8a2fd6,0xba2f3b0e,0xb89b3bf1,
0x2e46bba8,0x2648bb25,0x3bf6b4a5,0x3bffb732,0xb6d7b81d,0xbb253303,0x3b3bbadd,0x3732bbce,0xb95f3bea,0xb4443b50,0xb9edb0b2,0xbbb6367c,
0x3b88b3c6,0x3bfab89b,0xb5643bc3,0xacb53a8a,0xaa48ba6d,0xafd6b984,0x3bfeb8c4,0x3bf1b9cb,0xbbd93aa7,0xb93a3be2,0xb23eb872,0xba0f3179,
0x323e3872,0x38ec2648,0xbbd93aa7,0xba4f3bff,0x3bd9baa7,0x3b25bbce,0x323e3872,0x37323303,0xb23eb872,0xb444b67c,0x3bd9baa7,0x3bb6bb50,
0xaa4838c4,0x389bafd6,0xbbfe3a6d,0xba8a3bf1,0x3b3bb81d,0x3bffbb25,0xb6d73add,0x26483732,0x39edbbea,0x3848baf6,0x395fb0b2,0x3ac2b7e3,
0xb564b3c6,0xb67cacb5,0x3b88bbc3,0x3b50bbfa,0x3ba8ba2f,0x3b77bbfa,0xb4a53913,0x35c2acb5,0x3b0ebbf6,0x389bba4f,0x378bae46,0x3a8ab8ec,
0x34a5b913,0x2648b505,0x3ba8ba2f,0x3bffbb99,0xb78b2e46,0xb8483444,0x3b0ebbf6,0x3ac2bbb6,0x381db95f,0xafd62648,0x3addb9ed,0x3bf1bbff,
0x30b2b564,0xb5053303,0x3beabb88,0x3b99bbce,0xb3c62a48,0xb7e3367c,0x3bc3bbfe,0x3af6bb50,0xb8c436d7,0xb93a389b,0x3a6dbb3b,0x3a0fba8a,
0xb9a839a8,0xbbf13bff,0x39a8b9a8,0x2fd6a648,0xb9a839a8,0xbb993bce,0x39a8b9a8,0x3505b303,0xb9a839a8,0xbaf63b50,0x39a8b9a8,0x37e3b67c,
0xb9a839a8,0xba0f3a8a,0x39a8b9a8,0x393ab89b,0xbadd39ed,0xb5c22cb5,0xb81d395f,0xbb773bfa,0xbbea3b88,0xba8a38ec,0xb0b23564,0xb89b3a4f,
0xbbc33bfe,0xbbff3b99,0x33c6aa48,0xa6483505,0xba6d3b3b,0xbac23bb6,0x38c4b6d7,0x3848b444,0x34a5b913,0x3a8abbf1,0xbba83a2f,0xb89b2fd6,
0xb78b2e46,0xa648b732,0xbb0e3bf6,0xbbff3b25,0xbba83a2f,0xbac237e3,0xb4a53913,0xb8483af6,0xbb0e3bf6,0xbb503bfa,0x378bae46,0x367c2cb5,
0x3bfeba6d,0x3a0fb179,0x2a48b8c4,0x393abbe2,0x36d7badd,0x3a4fbbff,0xbb3b381d,0xb8eca648,0xb95f30b2,0xb732b303,0xb9ed3bea,0xbb253bce,
0xbb883bc3,0xbbb63b50,0x356433c6,0x3444367c,0x323e3872,0xb7323bce,0x3bd9baa7,0x3b25b303,0x3bd9baa7,0x3bb6b67c,0xb23eb872,0x3444bb50,
0xb23eb872,0x2cb5ba8a,0xbbd93aa7,0xbbfa389b,0xbbd93aa7,0xbbf139cb,0x323e3872,0x2fd63984,0xbb3b3add,0xbbce3444,0x36d7381d,0xb3033bb6,
0x39ed30b2,0x35c2393a,0x395fbbea,0x3b77ba0f,0x3564bbc3,0x389bbbf1,0xbb8833c6,0xba8aafd6,0xbbfe38c4,0xbbff3732,0x2a483a6d,0xa6483b25,
0xb913b78b,0xa648bb99,0xba2f3b0e,0xbbff3505,0xae463ba8,0xb8483bb6,0x3bf6b4a5,0x3ac23444,0x3a2fbb0e,0x3b50b93a,0xb913b78b,0xb67cba0f,
0xbbf634a5,0xbbe22fd6,0xae463ba8,0xb1793bf1,0x38c4bb3b,0x3bb6b5c2,0xba6db6d7,0xb444bb77,0xbadd395f,0xbbfa3179,0x381d39ed,0x2cb53be2,
0x3beab564,0x3bf12648,0xb0b2bb88,0x2fd6bbff,0xbbc3aa48,0xbb99b303,0xb3c63bfe,0xb5053bce,0x3b64361f,0x37e33b50,0x361fbb64,0x3af6b67c,
0xbb64b61f,0xb93aba8a,0xb61f3b64,0xba0f389b,0x3b64361f,0x3a4f3984,0x361fbb64,0x38ecb9cb,0xbb64b61f,0xbb25b848,0xb61f3b64,0xb7323ac2,
0xb0b23b88,0xb9cb3732,0x3bea3564,0x39843b25,0xb3c6bbfe,0x3303baf6,0xbbc32a48,0xbbceb7e3,0x38c43b3b,0x35c23bfa,0x3a6db6d7,0x3b77acb5,
0xbaddb95f,0xba8aba4f,0xb81d39ed,0xb89b38ec,0xbbf6b4a5,0xbac2baf6,0x2e463ba8,0xb84837e3,0x3913b78b,0x3b502cb5,0xba2fbb0e,0xb67cbbfa,
0x2e463ba8,0xb1793a4f,0x3bf634a5,0x3be238ec,0xba2fbb0e,0xb9cbbb99,0xb913378b,0xb9843505,0xb564bbc3,0x3505b848,0xbb88b3c6,0xbb99bac2,
0x3bfe38c4,0x3af63b77,0x2a48ba6d,0x37e3b5c2,0xb6d7381d,0xb93a3179,0x3b3b3add,0x3a0f3be2,0xb95fbbea,0xb8ecbbff,0xb9ed30b2,0xba4fa648,
0x3aa7323e,0x3bfa3a8a,0xb872bbd9,0x2cb5b89b,0x38723bd9,0x2fd639cb,0x3aa7323e,0x3bf13984,0xbaa7b23e,0xbb99b848,0x38723bd9,0x35053ac2,
0xb872bbd9,0xb7e3bb77,0xbaa7b23e,0xbaf6b5c2,0x39ed3bea,0x317938ec,0x395f30b2,0x3be23a4f,0xb56433c6,0xb9cbb505,0x3b883bc3,0x39843b99,
0xbbfeba6d,0xbbcebbb6,0x2a4838c4,0xb3033444,0xb6d7badd,0xb5c2ba0f,0xbb3bb81d,0xbb77b93a,0xb78bae46,0xbb50ba0f,0x3b0e3bf6,0x367c393a,
0xbba8ba2f,0xbbe2bbf1,0x34a53913,0xb1792fd6,0xbb0ebbf6,0xb9cbbb25,0xb78bae46,0xb984b732,0xb4a5b913,0xb303b7e3,0xbba8ba2f,0xbbcebaf6,
0xbbc3bbfe,0xb8ecb984,0xb3c6aa48,0xba4fb9cb,0xba6dbb3b,0xb732b848,0xb8c4b6d7,0xbb25bac2,0xb81db95f,0xb444b5c2,0xbaddb9ed,0xbbb6bb77,
0xb0b2b564,0xacb5b179,0xbbeabb88,0xbbfabbe2,0x3c003c00,0x96480000,0x3c003c00,0xa311a248,0x3c003c00,0x9cb69a48,0x3c003c00,0xa452a3db,
0x3c003c00,0x9fdb9e48,0x3c003c00,0xa51ba4b6,0x3c003c00,0xa17fa0b6,0x3bff3c00,0xa5e4a57f,0x3c003c00,0x9fdb0000,0x3bfb3bfc,0xac6aabd9,
0x3bff3c00,0xa5e4a3db,0x3bf93bfa,0xad65ace7,0x3bfe3bff,0xa8e8a7da,0x3bf63bf7,0xae5fade2,0x3bfd3bfe,0xaadea9e3,0x3bf23bf4,0xaf59aedc,
0x3c003c00,0xa3110000,0x3bf03bf4,0xafefaf0e,0x3bfe3bff,0xa94da711,0x3be83bed,0xb0d7b067,0x3bfb3bfd,0xac6aab11,0x3bdf3be4,0xb1b6b147,
0x3bf63bf9,0xae2dad4c,0x3bd43bda,0xb294b226,0x3c003c00,0xa51b0000,0x3bdf3be6,0xb1b6b115,0x3bfc3bfe,0xaba7a91b,0x3bcf3bd7,0xb2f7b257,
0x3bf63bf9,0xae5fad1a,0x3bbc3bc6,0xb41ab396,0x3bec3bf1,0xb074afa4,0x3ba53bb1,0xb4b7b469,0x3bff3c00,0xa6ad0000,0x3bc83bd4,0xb371b2a1,
0x3bfa3bfd,0xad00aaac,0x3bac3bbb,0xb487b420,0x3bef3bf5,0xb029aeaa,0x3b8b3b9d,0xb552b4ed,0x3bde3be7,0xb1cfb0fd,0x3b653b79,0xb61ab5b6,
0x3bff3c00,0xa81f0000,0x3bab3bbc,0xb493b414,0x3bf63bfc,0xae2dac1f,0x3b813b97,0xb58db511,0x3be53bef,0xb122b01d,0x3b4f3b69,0xb682b608,
0x3bcc3bda,0xb328b226,0x3b163b33,0xb76fb6f9,0x3bfe3c00,0xa8e80000,0x3b873ba0,0xb56ab4d5,0x3bf23bfa,0xaf59ace7,0x3b4c3b6b,0xb68db5fd,
0x3bda3be8,0xb219b0e4,0x3b073b2b,0xb7a6b71b,0x3bb73bca,0xb43eb34c,0x3ab63ae0,0xb85ab817,0x3bfe3c00,0xa9b10000,0x3b5e3b80,0xb63cb593,
0x3bee3bf8,0xb042adb0,0x3b103b39,0xb785b6e3,0x3bce3be0,0xb30fb1aa,0x3ab33ae3,0xb85fb812,0x3b9e3bb7,0xb4e7b438,0x3a493a7f,0xb8f3b8ab,
0x3bfd3c00,0xaa7a0000,0x3b2f3b5a,0xb70ab64e,0x3be83bf6,0xb0d7ae78,0x3acb3aff,0xb83ab7c2,0x3bbf3bd6,0xb402b26f,0x3a543a92,0xb8e5b891,
0x3b813ba2,0xb58db4c9,0x39cd3a13,0xb982b935,0x3bfd3c00,0xab430000,0x3afb3b30,0xb7d2b705,0x3be23bf3,0xb16caf40,0x3a7e3abf,0xb8adb84d,
0x3bae3bcb,0xb47bb334,0x39eb3a37,0xb962b909,0x3b603b8a,0xb631b558,0x3946399b,0xba04b9b5,0x3bfc3c00,0xac060000,0x3ac13b02,0xb84ab7b7,
0x3bdc3bf0,0xb201b004,0x3a293a78,0xb91bb8b5,0x3b9c3bc0,0xb4f3b3f7,0x397939d4,0xb9d6b97b,0x3b3d3b70,0xb6d2b5e5,0x38b23918,0xba7aba2b,
0x3bfb3c00,0xac6a0000,0x3a813ad0,0xb8a8b832,0x3bd43bed,0xb294b067,0x39cd3a2b,0xb982b918,0x3b873bb2,0xb56ab45d,0x38fd3969,0xba41b9e5,
0x3b163b53,0xb76fb670,0x3815388c,0xbae1ba95,0x3bfa3c00,0xacce0000,0x3a3d3a99,0xb902b887,0x3bcc3be9,0xb328b0cb,0x396b39d8,0xb9e3b976,
0x3b713ba4,0xb5dfb4bd,0x387a38f6,0xbaa2ba47,0x3aeb3b33,0xb805b6f9,0x36dd37ee,0xbb3abaf3,0x3bf93c00,0xad330000,0x39f43a5e,0xb958b8d8,
0x3bc33be5,0xb3bab12e,0x39023980,0xba3db9d0,0x3b593b95,0xb654b51d,0x37dd387c,0xbaf7baa0,0x3abd3b11,0xb850b780,0x358136b5,0xbb83bb43,
0x3bf83c00,0xad970000,0x39a63a1f,0xb9aab927,0x3bba3be1,0xb426b191,0x38943922,0xba90ba23,0x3b3f3b84,0xb6c6b57c,0x36bb37f9,0xbb42baf0,
0x3a8c3aed,0xb899b802,0x341a3570,0xbbbcbb86,0x3bf73c00,0xadfb0000,0x395439dc,0xb9f8b972,0x3bb03bdc,0xb46fb1f4,0x382038bf,0xbadbba71,
0x3b243b72,0xb737b5da,0x358d36ee,0xbb81bb36,0x3a583ac6,0xb8e0b842,0x31533420,0xbbe3bbbb,0x3bf63c00,0xae5f0000,0x38fd3996,0xba41b9ba,
0x3ba53bd7,0xb4b7b257,0x374e3858,0xbb1ebab8,0x3b073b5f,0xb7a6b637,0x345735da,0xbbb3bb72,0x3a213a9c,0xb924b881,0x2cce3191,0xbbfabbe1,
0x3bf53c00,0xaec30000,0x38a3394d,0xba85b9fe,0x3b9a3bd2,0xb4ffb2b9,0x365437d8,0xbb59baf9,0x3ae83b4b,0xb80ab693,0x323234bd,0xbbd9bba4,
0x39e73a71,0xb966b8bf,0xa4522db0,0xbc00bbf8,0x3bf33c00,0xaf270000,0x38453900,0xbac4ba3f,0x3b8e3bcd,0xb546b31b,0x355236f9,0xbb8bbb33,
0x3ac73b36,0xb840b6ee,0x2f593334,0xbbf2bbcb,0x39aa3a43,0xb9a6b8fb,0xaef51a48,0xbbf4bc00,0x3bf23c00,0xaf8b0000,0x37c838b0,0xbafeba7c,
0x3b813bc7,0xb58db37d,0x344b3614,0xbbb5bb67,0x3aa53b20,0xb874b748,0x288430e4,0xbbffbbe8,0x396b3a13,0xb9e3b935,0xb263ad4c,0xbbd7bbf9,
0x3bf03c00,0xafef0000,0x36ff385d,0xbb32bab5,0x3b733bc1,0xb5d4b3df,0x327c3529,0xbbd6bb93,0x3a813b08,0xb8a8b7a1,0xa9b12d1a,0xbbfebbf9,
0x392939e1,0xba1db96d,0xb49fb160,0xbba9bbe3,0x3bef3c00,0xb0290000,0x36313807,0xbb60bae9,0x3b653bbb,0xb61ab420,0x305b3438,0xbbedbbb7,
0x3a5c3af0,0xb8dbb7f9,0xafef1e48,0xbbf0bc00,0x38e539ad,0xba54b9a4,0xb602b408,0xbb6abbbe,0x3bed3c00,0xb05b0000,0x355e375e,0xbb89bb1a,
0x3b573bb4,0xb65fb451,0x2c6a3288,0xbbfbbbd5,0x3a353ad6,0xb90cb828,0xb27cac51,0xbbd6bbfb,0x389e3976,0xba89b9d8,0xb759b558,0xbb1bbb8a,
0x3beb3c00,0xb08d0000,0x348736aa,0xbbacbb46,0x3b473bad,0xb6a4b481,0x16483099,0xbc00bbeb,0x3a0d3abc,0xb93cb852,0xb47bb080,0xbbaebbec,
0x3855393e,0xbababa0b,0xb850b69e,0xbabdbb49,0x3be93c00,0xb0be0000,0x335935f1,0xbbc9bb6e,0x3b373ba6,0xb6e8b4b1,0xac382d4c,0xbbfcbbf9,
0x39e33aa0,0xb96bb87c,0xb5b1b2d2,0xbb7abbd1,0x380a3905,0xbae8ba3b,0xb8eab7d8,0xba50baf9,0x3be73c00,0xb0f00000,0x319e3534,0xbbe0bb91,
0x3b273b9e,0xb72cb4e1,0xb042257f,0xbbeebc00,0x39b83a83,0xb999b8a6,0xb6ddb48d,0xbb3abbab,0x377a38c9,0xbb13ba69,0xb979b881,0xb9d6ba9c,
0x3be53c00,0xb1220000,0x2fbd3475,0xbbf1bbaf,0x3b163b97,0xb76fb511,0xb263a91b,0xbbd7bbfe,0x398b3a65,0xb9c5b8ce,0xb7feb5ab,0xbaeebb7b,
0x36dd388c,0xbb3aba95,0xb9fcb90e,0xb94fba33,0x3be33c00,0xb1530000,0x2c383365,0xbbfcbbc9,0x3b043b8f,0xb7b2b540,0xb43eae78,0xbbb7bbf6,
0x395d3a47,0xb9f0b8f6,0xb889b6c1,0xba97bb41,0x363c384d,0xbb5ebabf,0xba73b992,0xb8bcb9be,0x3be13c00,0xb1850000,0x217f31db,0xbc00bbdd,
0x3af13b86,0xb7f3b570,0xb546b12e,0xbb8ebbe5,0x392e3a27,0xba19b91d,0xb90cb7cd,0xba35bafc,0x3599380d,0xbb7fbae6,0xbadbba0b,0xb820b93e,
0x3bdf3c00,0xb1b60000,0xa9b1304e,0xbbfebbed,0x3ade3b7d,0xb81ab59f,0xb648b31b,0xbb5cbbcd,0x38fd3a07,0xba41b943,0xb986b867,0xb9c9baae,
0x34f33796,0xbb9cbb0b,0xbb35ba78,0xb6f4b8b5,0x3bdd3c00,0xb1e80000,0xae5f2d7e,0xbbf6bbf8,0x3acb3b74,0xb83ab5ce,0xb742b481,0xbb21bbad,
0x38cc39e5,0xba67b969,0xb9f8b8e2,0xb954ba56,0x344b3710,0xbbb5bb2e,0xbb7fbad9,0xb599b822,0x3bda3c00,0xb2190000,0xb0f028b6,0xbbe7bbff,
0x3ab63b6b,0xb85ab5fd,0xb81ab570,0xbadebb86,0x389939c3,0xba8cb98d,0xba60b956,0xb8d6b9f6,0x33403687,0xbbcbbb4e,0xbbb8bb2e,0xb432b710,
0x3bff3bff,0xa6ada648,0x3bfe3bff,0xa8e8a8b6,0x3bff3bff,0xa776a711,0x3bfe3bfe,0xa94da91b,0x3bff3bff,0xa81fa7da,0x3bfe3bfe,0xa9b1a97f,
0x3bff3bff,0xa884a852,0x3bfe3bfe,0xaa16a9e3,0x3bef3bf1,0xb029afd6,0x3bda3bdd,0xb219b1db,0x3bea3bed,0xb0a6b067,0x3bd43bd7,0xb294b257,
0x3be53be8,0xb122b0e4,0x3bce3bd1,0xb30fb2d2,0x3be03be3,0xb19eb160,0x3bc63bca,0xb389b34c,0x3bc83bce,0xb371b303,0x3b873b91,0xb56ab534,
0x3bba3bc1,0xb426b3df,0x3b733b7d,0xb5d4b59f,0x3bab3bb2,0xb493b45d,0x3b5e3b69,0xb63cb608,0x3b9a3ba2,0xb4ffb4c9,0x3b473b53,0xb6a4b670,
0x3b8b3b99,0xb552b505,0x3b073b1a,0xb7a6b75e,0x3b6f3b7d,0xb5ebb59f,0x3ade3af3,0xb81ab7ee,0x3b4f3b5f,0xb682b637,0x3ab33ac9,0xb85fb83d,
0x3b2c3b3e,0xb715b6cc,0x3a853a9c,0xb8a3b881,0x3b3a3b50,0xb6ddb67c,0x3a5c3a7c,0xb8dbb8b0,0x3b0a3b22,0xb79bb73d,0x3a193a3b,0xb92eb905,
0x3ad53af0,0xb82ab7f9,0x39d239f6,0xb97db956,0x3a9b3ab8,0xb884b858,0x398639ad,0xb9c9b9a4,0x3ad53af6,0xb82ab7e3,0x398b39ba,0xb9c5b996,
0x3a8c3ab1,0xb899b862,0x3929395b,0xba1db9f2,0x3a3d3a65,0xb902b8ce,0x38c138f6,0xba6fba47,0x39e73a13,0xb966b935,0x3855388c,0xbababa95,
0x3a5c3a8a,0xb8dbb89b,0x389938d8,0xba8cba5e,0x39f83a2b,0xb954b918,0x38153858,0xbae1bab8,0x398b39c3,0xb9c5b98d,0x371537a1,0xbb2cbb08,
0x39163951,0xba2db9fa,0x35f73687,0xbb6cbb4e,0x39d23a0f,0xb97db93a,0x371537b7,0xbb2cbb02,0x394f3992,0xb9fcb9be,0x35c83670,0xbb76bb53,
0x38c13909,0xba6fba37,0x346f351d,0xbbb0bb95,0x382a3877,0xbad5baa3,0x3219337d,0xbbdabbc7,0x39373984,0xba11b9cb,0x34cf3593,0xbba1bb80,
0x389438e7,0xba90ba52,0x327c3408,0xbbd6bbbe,0x37c8383d,0xbafebac9,0x2e9130e4,0xbbf5bbe8,0x36543710,0xbb59bb2e,0x16482aac,0xbc00bbfd,
0x388e38ec,0xba93ba4f,0x30d732a1,0xbbe8bbd4,0x3790382d,0xbb0dbad3,0x28e82e14,0xbbfebbf7,0x35eb36c1,0xbb6fbb41,0xaccea4b6,0xbbfabc00,
0x34323511,0xbbb8bb97,0xb201b036,0xbbdcbbee,0x37b23848,0xbb04bac2,0x96482bd9,0xbc00bbfc,0x35df36cc,0xbb71bb3e,0xb010ac1f,0xbbefbbfc,
0x33eb34ed,0xbbc0bb9d,0xb402b20d,0xbbbfbbdb,0x2fef31f4,0xbbf0bbdc,0xb5ebb4f9,0xbb6fbb9b,0x36313732,0xbb60bb25,0xb0f0ad7e,0xbbe7bbf8,
0x341a3529,0xbbbcbb93,0xb49fb31b,0xbba9bbcd,0x2fbd320d,0xbbf1bbdb,0xb6afb5ab,0xbb45bb7b,0xa4522aac,0xbc00bbfd,0xb850b7ac,0xbabdbb05,
0x349f35c2,0xbba9bb77,0xb4dbb365,0xbb9fbbc9,0x308d32ea,0xbbebbbd0,0xb715b5fd,0xbb2cbb6b,0x9fdb2c51,0xbc00bbfb,0xb894b812,0xba90bae3,
0xb109ad4c,0xbbe6bbf9,0xb982b90e,0xb9cdba33,0x32013444,0xbbdcbbb6,0xb721b5f1,0xbb2abb6e,0x26ad2edc,0xbbffbbf4,0xb8adb822,0xba7ebad9,
0xb05bab11,0xbbedbbfd,0xb9aab930,0xb9a6ba17,0xb4b7b2ea,0xbba5bbd0,0xba81ba1b,0xb8a8b92b,0x2d653179,0xbbf9bbe2,0xb89eb807,0xba89bae9,
0xadc99a48,0xbbf8bc00,0xb9afb92b,0xb9a1ba1b,0xb432b1aa,0xbbb8bbe0,0xba93ba27,0xb88eb91d,0xb6d2b587,0xbb3dbb82,0xbb45baf3,0xb6afb7ee,
0xa51b2cb5,0xbc00bbfa,0xb990b900,0xb9c0ba3f,0xb294af40,0xbbd4bbf3,0xba89ba13,0xb89eb935,0xb625b4bd,0xbb63bba4,0xbb47baf0,0xb6a4b7f9,
0xb865b780,0xbab0bb11,0xbbc5bb8f,0xb3a2b540,0xafefa648,0xbbf0bbff,0xba60b9dc,0xb8d6b972,0xb517b31b,0xbb96bbcd,0xbb35bad3,0xb6f4b82d,
0xb7feb693,0xbaeebb4b,0xbbc0bb84,0xb3ebb57c,0xb94ab8ab,0xba00ba7f,0xbbfdbbe9,0xaa7ab0cb,0xb340afd6,0xbbcbbbf1,0xbb0aba99,0xb79bb887,
0xb6d2b540,0xbb3dbb8f,0xbbaebb67,0xb47bb614,0xb8dbb828,0xba5cbad6,0xbbfbbbe0,0xac9cb1aa,0xba15b980,0xb933b9d0,0xbbecbbff,0x30742852,
0xb53ab303,0xbb90bbce,0xbb89bb30,0xb55eb705,0xb83ab6e3,0xbacbbb39,0xbbf2bbca,0xaf8bb34c,0xb9a1b8f6,0xb9afba47,0xbbf5bc00,0x2ec39e48,
0xbac1ba3b,0xb84ab905,0xbb92bbd0,0x352f32ea,0xb6c6b505,0xbb3fbb99,0xbbdcbba0,0xb201b4d5,0xb8fdb838,0xba41bacc,0xbbfebbfb,0x2a16ac83,
0xba50b9b1,0xb8eab99f,0xbbaebbe4,0x347b3147,0xbb4abad9,0xb699b822,0xbaf1bb5d,0x37f33642,0xb820b67c,0xbadbbb50,0xbbffbbe6,0xa884b115,
0xb9afb8f1,0xb9a1ba4b,0xbbd2bbf8,0x32c62db0,0xbae5ba56,0xb80fb8e2,0xbb2abb8c,0x3721354c,0xbbaebb58,0xb47bb659,0xba11baaa,0x3937386d,
0xb8d1b7e3,0xba64baf6,0xbbf2bc00,0x2f8ba248,0xba4db99b,0xb8eeb9b5,0xbb6fbbc1,0x35eb33df,0xbb5cbae3,0xb648b812,0xba6bbafc,0x38c737cd,
0xbbebbbb4,0xb08db451,0xb8f8b9be,0x3a453992,0xb974b89b,0xb9daba8a,0xbbb5bbed,0x344b304e,0xbad5ba33,0xb82ab90e,0xbad8bb58,0x38253659,
0xbbb3bb55,0xb457b665,0xb979ba37,0x39d63909,0xbc00bbed,0x9648b067,0xb764b8a0,0x3b183a87,0xba09b93a,0xb941ba0f,0xbb4abbaf,0x36993475,
0xbb45bab8,0xb6afb858,0xba11babf,0x3937384d,0xbbeabbab,0xb0a6b48d,0xb85ab943,0x3ab63a07,0xbbecbc00,0x30749a48,0xb493b6b5,0x3bab3b43,
0xba8cb9cb,0xb899b984,0xbab3bb46,0x385f36aa,0xbb9cbb28,0xb4f3b726,0xb91fb9fa,0x3a253951,0xbc00bbe4,0xa452b147,0xb631b828,0x3b603ad6,
0xbbb0bbee,0x346f3036,0xae5fb3df,0x3bf63bc1,0xbafeba4f,0xb7c8b8ec,0xb9f4bab5,0x3958385d,0xbbd8bb82,0xb24bb587,0xb80ab90e,0x3ae83a33,
0xbbf3bbfe,0x2f27a97f,0xb2f7b5da,0x3bcf3b72,0xbb4cbbb7,0x368d3438,0x2dc9ac1f,0x3bf83bfc,0xbb5cbac2,0xb648b848,0xb911b9fe,0x3a31394d,
0xbbf9bbc4,0xad33b3ae,0xb5b1b802,0x3b7a3aed,0xbbc5bbf9,0x33a22d1a,0xa94db26f,0x3bfe3bd6,0xbac4bb5d,0x38453642,0x346f2fa4,0x3bb03bf1,
0xbba5bb25,0xb4b7b732,0xb80fb927,0x3ae53a1f,0xbbffbbee,0x2884b036,0xb24bb5b6,0x3bd83b79,0xbb76bbd6,0x35c8326f,0x305ba7da,0x3bed3bff,
0xba19bae0,0x392e3817,0x374234c9,0x3b213ba2,0xbbd9bb77,0xb232b5c2,0xb5ebb832,0x3b6f3ad0,0xbbe8bc00,0x30d7a57f,0xa81fb288,0x3bff3bd5,
0xbb07bb95,0x37a6351d,0x34f33080,0x3b9c3bec,0xb94fba43,0x39fc38fb,0x38ea3780,0x3a503b11,0xbbf8bbb6,0xadc9b444,0xb328b64e,0x3bcc3b5a,
0xbbb7bbf8,0x343e2db0,0x3042a9e3,0x3bee3bfe,0xba7abb36,0x38b236ee,0x379034ed,0x3b0d3b9d,0xb86ab989,0x3aac39c7,0x3a0438fb,0x39463a43,
0xbc00bbe2,0x2311b179,0xac9cb414,0x3bfb3bbc,0xbb6abbd7,0x36023257,0x34b72f40,0x3ba53bf3,0xb9d2babc,0x397d3852,0x38f83775,0x3a453b14,
0xb6ddb8b5,0x3b3a3a78,0x3ae83a0b,0x380a393e,0xbbf2bbfa,0x2f8bacb5,0x2d33af0e,0x3bf93bf4,0xbb04bb9e,0x37b234e1,0x372c3451,0x3b273bb4,
0xb911ba27,0x3a31391d,0x3a0038e2,0x394a3a56,0xb4c3b796,0x3ba33b0b,0x3b8b3ae6,0x3552380d,0x4c004c00,0x26480000,0x4c004c00,0x33113248,
0x4c004c00,0x2cb62a48,0x4c004c00,0x345233db,0x4c004c00,0x2fdb2e48,0x4c004c00,0x351b34b6,0x4c004c00,0x317f30b6,0x4bff4c00,0x35e4357f,
0x4c004c00,0x2fdb0000,0x4bfb4bfc,0x3c6a3bd9,0x4bff4c00,0x35e433db,0x4bf94bfa,0x3d653ce7,0x4bfe4bff,0x38e837da,0x4bf64bf7,0x3e5f3de2,
0x4bfd4bfe,0x3ade39e3,0x4bf24bf4,0x3f593edc,0x4c004c00,0x33110000,0x4bf04bf4,0x3fef3f0e,0x4bfe4bff,0x394d3711,0x4be84bed,0x40d74067,
0x4bfb4bfd,0x3c6a3b11,0x4bdf4be4,0x41b64147,0x4bf64bf9,0x3e2d3d4c,0x4bd44bda,0x42944226,0x4c004c00,0x351b0000,0x4bdf4be6,0x41b64115,
0x4bfc4bfe,0x3ba7391b,0x4bcf4bd7,0x42f74257,0x4bf64bf9,0x3e5f3d1a,0x4bbc4bc6,0x441a4396,0x4bec4bf1,0x40743fa4,0x4ba54bb1,0x44b74469,
0x4bff4c00,0x36ad0000,0x4bc84bd4,0x437142a1,0x4bfa4bfd,0x3d003aac,0x4bac4bbb,0x44874420,0x4bef4bf5,0x40293eaa,0x4b8b4b9d,0x455244ed,
0x4bde4be7,0x41cf40fd,0x4b654b79,0x461a45b6,0x4bff4c00,0x381f0000,0x4bab4bbc,0x44934414,0x4bf64bfc,0x3e2d3c1f,0x4b814b97,0x458d4511,
0x4be54bef,0x4122401d,0x4b4f4b69,0x46824608,0x4bcc4bda,0x43284226,0x4b164b33,0x476f46f9,0x4bfe4c00,0x38e80000,0x4b874ba0,0x456a44d5,
0x4bf24bfa,0x3f593ce7,0x4b4c4b6b,0x468d45fd,0x4bda4be8,0x421940e4,0x4b074b2b,0x47a6471b,0x4bb74bca,0x443e434c,0x4ab64ae0,0x485a4817,
0x4bfe4c00,0x39b10000,0x4b5e4b80,0x463c4593,0x4bee4bf8,0x40423db0,0x4b104b39,0x478546e3,0x4bce4be0,0x430f41aa,0x4ab34ae3,0x485f4812,
0x4b9e4bb7,0x44e74438,0x4a494a7f,0x48f348ab,0x4bfd4c00,0x3a7a0000,0x4b2f4b5a,0x470a464e,0x4be84bf6,0x40d73e78,0x4acb4aff,0x483a47c2,
0x4bbf4bd6,0x4402426f,0x4a544a92,0x48e54891,0x4b814ba2,0x458d44c9,0x49cd4a13,0x49824935,0x4bfd4c00,0x3b430000,0x4afb4b30,0x47d24705,
0x4be24bf3,0x416c3f40,0x4a7e4abf,0x48ad484d,0x4bae4bcb,0x447b4334,0x49eb4a37,0x49624909,0x4b604b8a,0x46314558,0x4946499b,0x4a0449b5,
0x4bfc4c00,0x3c060000,0x4ac14b02,0x484a47b7,0x4bdc4bf0,0x42014004,0x4a294a78,0x491b48b5,0x4b9c4bc0,0x44f343f7,0x497949d4,0x49d6497b,
0x4b3d4b70,0x46d245e5,0x48b24918,0x4a7a4a2b,0x4bfb4c00,0x3c6a0000,0x4a814ad0,0x48a84832,0x4bd44bed,0x42944067,0x49cd4a2b,0x49824918,
0x4b874bb2,0x456a445d,0x48fd4969,0x4a4149e5,0x4b164b53,0x476f4670,0x4815488c,0x4ae14a95,0x4bfa4c00,0x3cce0000,0x4a3d4a99,0x49024887,
0x4bcc4be9,0x432840cb,0x496b49d8,0x49e34976,0x4b714ba4,0x45df44bd,0x487a48f6,0x4aa24a47,0x4aeb4b33,0x480546f9,0x46dd47ee,0x4b3a4af3,
0x4bf94c00,0x3d330000,0x49f44a5e,0x495848d8,0x4bc34be5,0x43ba412e,0x49024980,0x4a3d49d0,0x4b594b95,0x4654451d,0x47dd487c,0x4af74aa0,
0x4abd4b11,0x48504780,0x458146b5,0x4b834b43,0x4bf84c00,0x3d970000,0x49a64a1f,0x49aa4927,0x4bba4be1,0x44264191,0x48944922,0x4a904a23,
0x4b3f4b84,0x46c6457c,0x46bb47f9,0x4b424af0,0x4a8c4aed,0x48994802,0x441a4570,0x4bbc4b86,0x4bf74c00,0x3dfb0000,0x495449dc,0x49f84972,
0x4bb04bdc,0x446f41f4,0x482048bf,0x4adb4a71,0x4b244b72,0x473745da,0x458d46ee,0x4b814b36,0x4a584ac6,0x48e04842,0x41534420,0x4be34bbb,
0x4bf64c00,0x3e5f0000,0x48fd4996,0x4a4149ba,0x4ba54bd7,0x44b74257,0x474e4858,0x4b1e4ab8,0x4b074b5f,0x47a64637,0x445745da,0x4bb34b72,
0x4a214a9c,0x49244881,0x3cce4191,0x4bfa4be1,0x4bf54c00,0x3ec30000,0x48a3494d,0x4a8549fe,0x4b9a4bd2,0x44ff42b9,0x465447d8,0x4b594af9,
0x4ae84b4b,0x480a4693,0x423244bd,0x4bd94ba4,0x49e74a71,0x496648bf,0xb4523db0,0x4c004bf8,0x4bf34c00,0x3f270000,0x48454900,0x4ac44a3f,
0x4b8e4bcd,0x4546431b,0x455246f9,0x4b8b4b33,0x4ac74b36,0x484046ee,0x3f594334,0x4bf24bcb,0x49aa4a43,0x49a648fb,0xbef52a48,0x4bf44c00,
0x4bf24c00,0x3f8b0000,0x47c848b0,0x4afe4a7c,0x4b814bc7,0x458d437d,0x444b4614,0x4bb54b67,0x4aa54b20,0x48744748,0x388440e4,0x4bff4be8,
0x496b4a13,0x49e34935,0xc263bd4c,0x4bd74bf9,0x4bf04c00,0x3fef0000,0x46ff485d,0x4b324ab5,0x4b734bc1,0x45d443df,0x427c4529,0x4bd64b93,
0x4a814b08,0x48a847a1,0xb9b13d1a,0x4bfe4bf9,0x492949e1,0x4a1d496d,0xc49fc160,0x4ba94be3,0x4bef4c00,0x40290000,0x46314807,0x4b604ae9,
0x4b654bbb,0x461a4420,0x405b4438,0x4bed4bb7,0x4a5c4af0,0x48db47f9,0xbfef2e48,0x4bf04c00,0x48e549ad,0x4a5449a4,0xc602c408,0x4b6a4bbe,
0x4bed4c00,0x405b0000,0x455e475e,0x4b894b1a,0x4b574bb4,0x465f4451,0x3c6a4288,0x4bfb4bd5,0x4a354ad6,0x490c4828,0xc27cbc51,0x4bd64bfb,
0x489e4976,0x4a8949d8,0xc759c558,0x4b1b4b8a,0x4beb4c00,0x408d0000,0x448746aa,0x4bac4b46,0x4b474bad,0x46a44481,0x26484099,0x4c004beb,
0x4a0d4abc,0x493c4852,0xc47bc080,0x4bae4bec,0x4855493e,0x4aba4a0b,0xc850c69e,0x4abd4b49,0x4be94c00,0x40be0000,0x435945f1,0x4bc94b6e,
0x4b374ba6,0x46e844b1,0xbc383d4c,0x4bfc4bf9,0x49e34aa0,0x496b487c,0xc5b1c2d2,0x4b7a4bd1,0x480a4905,0x4ae84a3b,0xc8eac7d8,0x4a504af9,
0x4be74c00,0x40f00000,0x419e4534,0x4be04b91,0x4b274b9e,0x472c44e1,0xc042357f,0x4bee4c00,0x49b84a83,0x499948a6,0xc6ddc48d,0x4b3a4bab,
0x477a48c9,0x4b134a69,0xc979c881,0x49d64a9c,0x4be54c00,0x41220000,0x3fbd4475,0x4bf14baf,0x4b164b97,0x476f4511,0xc263b91b,0x4bd74bfe,
0x498b4a65,0x49c548ce,0xc7fec5ab,0x4aee4b7b,0x46dd488c,0x4b3a4a95,0xc9fcc90e,0x494f4a33,0x4be34c00,0x41530000,0x3c384365,0x4bfc4bc9,
0x4b044b8f,0x47b24540,0xc43ebe78,0x4bb74bf6,0x495d4a47,0x49f048f6,0xc889c6c1,0x4a974b41,0x463c484d,0x4b5e4abf,0xca73c992,0x48bc49be,
0x4be14c00,0x41850000,0x317f41db,0x4c004bdd,0x4af14b86,0x47f34570,0xc546c12e,0x4b8e4be5,0x492e4a27,0x4a19491d,0xc90cc7cd,0x4a354afc,
0x4599480d,0x4b7f4ae6,0xcadbca0b,0x4820493e,0x4bdf4c00,0x41b60000,0xb9b1404e,0x4bfe4bed,0x4ade4b7d,0x481a459f,0xc648c31b,0x4b5c4bcd,
0x48fd4a07,0x4a414943,0xc986c867,0x49c94aae,0x44f34796,0x4b9c4b0b,0xcb35ca78,0x46f448b5,0x4bdd4c00,0x41e80000,0xbe5f3d7e,0x4bf64bf8,
0x4acb4b74,0x483a45ce,0xc742c481,0x4b214bad,0x48cc49e5,0x4a674969,0xc9f8c8e2,0x49544a56,0x444b4710,0x4bb54b2e,0xcb7fcad9,0x45994822,
0x4bda4c00,0x42190000,0xc0f038b6,0x4be74bff,0x4ab64b6b,0x485a45fd,0xc81ac570,0x4ade4b86,0x489949c3,0x4a8c498d,0xca60c956,0x48d649f6,
0x43404687,0x4bcb4b4e,0xcbb8cb2e,0x44324710,0x4bd84c00,0x424b0000,0xc2adb248,0x4bd34c00,0x4aa24b62,0x487a462b,0xc88ec659,0x4a934b58,
0x4865499f,0x4ab049b1,0xcabdc9c3,0x4850498d,0x41e845fd,0x4bdd4b6b,0xcbe1cb74,0x418545ce,0x4bd64c00,0x427c0000,0xc432bbd9,0x4bb84bfc,
0x4a8c4b58,0x48994659,0xc8fdc73d,0x4a414b22,0x4830497b,0x4ad149d4,0xcb10ca27,0x4785491d,0x408d4570,0x4beb4b86,0xcbf9cbad,0x3d334481,
0x4bd34c00,0x42ad0000,0xc50bbf0e,0x4b984bf4,0x4a764b4e,0x48b74687,0xc966c80d,0x49e74ae6,0x47f34956,0x4af149f6,0xcb57ca83,0x465f48a6,
0x3e5f44e1,0x4bf64b9e,0xcc00cbd7,0xb17f4257,0x4bd04c00,0x42de0000,0xc5dfc115,0x4b714be6,0x4a604b43,0x48d646b5,0xc9c9c877,0x49864aa3,
0x47854930,0x4b104a17,0xcb92cad6,0x452f4828,0x3b434451,0x4bfd4bb4,0xcbf5cbf3,0xbe913f40,0x4bce4c00,0x430f0000,0xc6afc2a1,0x4b454bd4,
0x4a494b39,0x48f346e3,0xca25c8dd,0x491f4a5a,0x47154909,0x4b2c4a37,0xcbc0cb20,0x43eb4748,0x3311437d,0x4c004bc7,0xcbd9cbff,0xc2323711,
0x4bcb4c00,0x43400000,0xc77ac414,0x4b134bbc,0x4a314b2e,0x49114710,0xca7ac93e,0x48b24a0b,0x46a448e2,0x4b474a56,0xcbe2cb5f,0x416c4637,
0xb7764257,0x4bff4bd7,0xcbaccbfd,0xc487bb75,0x4bc84c00,0x43710000,0xc820c4d5,0x4adb4ba0,0x4a194b22,0x492e473d,0xcac7c99b,0x484049b5,
0x463148ba,0x4b604a74,0xcbf8cb95,0x3dc9451d,0xbc9c412e,0x4bfb4be5,0xcb6fcbeb,0xc5ebc099,0x4bc54c00,0x43a20000,0xc87fc593,0x4a9e4b80,
0x4a004b17,0x494a476a,0xcb0dc9f2,0x4790495b,0x45bc4891,0x4b784a92,0xcc00cbc0,0x317f43f7,0xbf594004,0x4bf24bf0,0xcb21cbca,0xc742c34c,
0x4bc24c00,0x43d30000,0xc8dbc64e,0x4a5c4b5a,0x49e74b0b,0x49664796,0xcb4aca43,0x469948fb,0x45464867,0x4b8e4aae,0xcbfbcbe0,0xbc6a41aa,
0xc1093db0,0x4be64bf8,0xcac4cb9b,0xc845c4f9,0x4bbf4c00,0x44020000,0xc933c705,0x4a154b30,0x49cd4aff,0x498247c2,0xcb7fca8e,0x45994896,
0x44cf483d,0x4ba14ac9,0xcbe9cbf5,0xc0be3eaa,0xc2633aac,0x4bd74bfd,0xca58cb5d,0xc8e0c642,0x4bbc4c00,0x441a0000,0xc986c7b7,0x49c94b02,
0x49b34af3,0x499d47ee,0xcbabcad3,0x4493482d,0x44574812,0x4bb34ae3,0xcbcbcbff,0xc34037da,0xc3ba33db,0x4bc34c00,0xc9dfcb11,0xc970c780,
0x4bb84c00,0x44320000,0xc9d6c832,0x49794ad0,0x49994ae6,0x49b8480d,0xcbcecb11,0x430f4780,0x43ba47cd,0x4bc34afc,0xcb9fcbfe,0xc4dbb97f,
0xc487b57f,0x4bac4c00,0xc958cab8,0xc9f4c858,0x4bb54c00,0x444b0000,0xca21c887,0x49244a99,0x497d4ad9,0x49d24822,0xcbe7cb49,0x40f0469e,
0x42c64775,0x4bd24b14,0xcb68cbf2,0xc60ebf72,0xc52fbb75,0x4b924bfd,0xc8c7ca52,0xca6bc8e7,0x4bb24c00,0x44630000,0xca67c8d8,0x48cc4a5e,
0x49624acc,0x49eb4838,0xcbf8cb79,0x3d9745b6,0x41cf471b,0x4bde4b2b,0xcb24cbdb,0xc737c20d,0xc5d4be14,0x4b734bf7,0xc82ac9e1,0xcad5c96d,
0x4bae4c00,0x447b0000,0xcaa9c927,0x486f4a1f,0x49464abf,0x4a04484d,0xcc00cba2,0x351b44c9,0x40d746c1,0x4be84b41,0xcad5cbb9,0xc82ac42c,
0xc676c036,0x4b524bee,0xc70ac964,0xcb2fc9e9,0x4bab4c00,0x44930000,0xcae5c972,0x480f49dc,0x49294ab1,0x4a1d4862,0xcbfecbc4,0xba1643ae,
0x3fbd4665,0x4bf14b55,0xca7acb8c,0xc8b2c54c,0xc715c160,0x4b2c4be3,0xc5b1c8dd,0xcb7aca5a,0x4ba74c00,0x44ab0000,0xcb1bc9ba,0x47594996,
0x490c4aa3,0x4a354877,0xcbf2cbdf,0xbf5941c3,0x3dc94608,0x4bf84b69,0xca15cb55,0xc933c665,0xc7b2c288,0x4b044bd5,0xc44bc84d,0xcbb5cabf,
0x4ba34c00,0x44c30000,0xcb4cc9fe,0x468d494d,0x48ee4a95,0x4a4d488c,0xcbdecbf1,0xc1cf3fa4,0x3ba745ab,0x4bfc4b7b,0xc9a6cb14,0xc9aac775,
0xc825c3ae,0x4ad84bc4,0xc1b6c76a,0xcbdfcb17,0x4b9f4c00,0x44db0000,0xcb78ca3f,0x45bc4900,0x48d14a87,0x4a6448a0,0xcbc0cbfd,0xc3eb3b75,
0x3776454c,0x4bff4b8c,0xc92ecac9,0xca19c83d,0xc86fc469,0x4aa94bb1,0xbd97c62b,0xcbf8cb62,0x4b9c4c00,0x44f30000,0xcb9eca7c,0x44e748b0,
0x48b24a78,0x4a7a48b5,0xcb9acc00,0xc4ffaa48,0xa64844ed,0x4c004b9d,0xc8adca74,0xca7ec8ba,0xc8b7c4f9,0x4a764b9b,0x2cb6c4e1,0xcc00cb9e,
0x4b984c00,0x450b0000,0xcbbdcab5,0x440e485d,0x48944a69,0x4a9048c9,0xcb6acbfc,0xc602bc1f,0xb81f448d,0x4bff4bab,0xc825ca17,0xcad8c930,
0xc8fdc587,0x4a414b82,0x3e2dc31b,0xcbf6cbcd,0x4b944c00,0x45230000,0xcbd7cae9,0x42634807,0x48744a5a,0x4aa548dd,0xcb32cbf0,0xc6ffc004,
0xbc06442c,0x4bfc4bb9,0xc72cc9b1,0xcb27c99f,0xc941c614,0x4a094b67,0x4201c067,0xcbdccbed,0x4b904c00,0x453a0000,0xcbeacb1a,0x40a6475e,
0x48554a4b,0x4aba48f1,0xcaf1cbdc,0xc7f3c1f4,0xbdfb4396,0x4bf74bc6,0xc602c943,0xcb6aca07,0xc982c69e,0x49cd4b49,0x446fbaac,0xcbb0cbfd,
0x4b8b4c00,0x45520000,0xcbf8cb46,0x3dc946aa,0x48354a3b,0x4ace4905,0xcaa9cbc1,0xc86fc3df,0xbfef42d2,0x4bf04bd1,0xc4cfc8ce,0xcba1ca65,
0xc9c0c726,0x49904b28,0x45d43852,0xcb73cbff,0x4b874c00,0x456a0000,0xcbffcb6e,0x388445f1,0x48154a2b,0x4ae14918,0xca58cb9e,0xc8e0c4e1,
0xc0f0420d,0x4be74bdb,0xc328c852,0xcbcccabc,0xc9fcc7ac,0x494f4b05,0x472c3fa4,0xcb27cbf1,0x4b834c00,0x45810000,0xcc00cb91,0xb51b4534,
0x47e84a1b,0x4af4492b,0xca00cb74,0xc94ac5ce,0xc1e84147,0x4bdd4be4,0xc0a6c7a1,0xcbeacb08,0xca35c817,0x490c4ae0,0x483a4288,0xcacbcbd5,
0x4b7f4c00,0x45990000,0xcbfacbaf,0xbcce4475,0x47a64a0b,0x4b07493e,0xc9a1cb43,0xc9afc6b5,0xc2de4080,0x4bd04bec,0xbc38c693,0xcbfccb4b,
0xca6bc858,0x48c74ab8,0x48d64499,0xca60cbaa,0x4b7a4c00,0x45b10000,0xcbefcbc9,0xc0294365,0x476449fa,0x4b184951,0xc93ccb0b,0xca0dc796,
0xc3d33f72,0x4bc24bf2,0x3311c57c,0xcc00cb84,0xca9ec896,0x487f4a8e,0x496645e5,0xc9e7cb70,0x4b764c00,0x45c80000,0xcbddcbdd,0xc1e841db,
0x472149e9,0x4b2a4964,0xc8d1cacc,0xca64c838,0xc4633de2,0x4bb24bf7,0x3dfbc45d,0xcbf7cbb2,0xcacec8d3,0x48354a62,0x49eb4726,0xc962cb28,
0x4b714c00,0x45df0000,0xcbc5cbed,0xc3a2404e,0x46dd49d8,0x4b3a4976,0xc85fca87,0xcab3c8a0,0xc4db3c51,0x4b9f4bfb,0x4185c26f,0xcbe1cbd6,
0xcafbc90e,0x47d24a33,0x4a64482d,0xc8d1cad3,0x4b6c4c00,0x45f70000,0xcba7cbf8,0xc4ab3d7e,0x469949c7,0x4b4a4989,0xc7d2ca3b,0xcafbc905,
0xc552397f,0x4b8b4bfe,0x4402c01d,0xcbbfcbef,0xcb24c948,0x47374a02,0x4ace48bf,0xc835ca71,0x4b684c00,0x460e0000,0xcb83cbff,0xc58138b6,
0x465449b5,0x4b59499b,0xc6ddc9e9,0xcb3ac964,0xc5c834b6,0x4b764c00,0x453abb11,0xcb90cbfd,0xcb4ac980,0x469949d0,0x4b2a4948,0xc721ca02,
0x2c002c00,0x2c002c00,0x2c002c00,0x2c002c00,0x2b642c00,0x261f29a8,0xa61f0000,0xab64a9a8,0x29a82c00,0xa9a80000,0xa9a8ac00,0x29a80000,
0x261f2c00,0xab64a9a8,0x2b640000,0xa61f29a8,0x2c00,0xac00,0x2c00,0xac00,0xa61f2c00,0x2b64a9a8,0xab640000,0x261f29a8,
0xa9a82c00,0x29a80000,0x29a8ac00,0xa9a80000,0xab642c00,0xa61f29a8,0x261f0000,0x2b64a9a8,0,0,0,0,
0x261f0000,0x2b6429a8,0x2b642c00,0x261f29a8,0x29a80000,0x29a82c00,0xa9a80000,0xa9a8ac00,0x2b640000,0xa61f29a8,0xa61fac00,0x2b6429a8,
0x2c000000,0xac000000,0x2c000000,0xac000000,0x2b640000,0xa61fa9a8,0xa61f2c00,0x2b64a9a8,0x29a80000,0x29a8ac00,0xa9a80000,0xa9a82c00,
0x261f0000,0x2b64a9a8,0x2b64ac00,0x261fa9a8,0xac002c00,0xac002c00,0xac002c00,0xac002c00,0xab642c00,0xa61f29a8,0x261f0000,0x2b64a9a8,
0xa9a82c00,0x29a80000,0x29a8ac00,0xa9a80000,0xa61f2c00,0x2b64a9a8,0xab640000,0x261f29a8,0x2c00,0xac00,0x2c00,0xac00,
0x261f2c00,0xab64a9a8,0x2b640000,0xa61f29a8,0x29a82c00,0xa9a80000,0xa9a8ac00,0x29a80000,0x2b642c00,0x261f29a8,0xa61f0000,0xab64a9a8,
0,0,0,0,0xa61f0000,0xab6429a8,0xab642c00,0xa61f29a8,0xa9a80000,0xa9a82c00,0x29a80000,0x29a8ac00,
0xab640000,0x261f29a8,0x261fac00,0xab6429a8,0xac000000,0x2c000000,0xac000000,0x2c000000,0xab640000,0x261fa9a8,0x261f2c00,0xab64a9a8,
0xa9a80000,0xa9a8ac00,0x29a80000,0x29a82c00,0xa61f0000,0xab64a9a8,0xab64ac00,0xa61fa9a8,0,0,0,0,
0xa61f0000,0xab64a9a8,0xab64ac00,0xa61fa9a8,0xa9a80000,0xa9a8ac00,0x29a80000,0x29a82c00,0xab640000,0x261fa9a8,0x261f2c00,0xab64a9a8,
0xac000000,0x2c000000,0xac000000,0x2c000000,0xab640000,0x261f29a8,0x261fac00,0xab6429a8,0xa9a80000,0xa9a82c00,0x29a80000,0x29a8ac00,
0xa61f0000,0xab6429a8,0xab642c00,0xa61f29a8,0x2c002c00,0x2c002c00,0x2c002c00,0x2c002c00,0x2b642c00,0x261f29a8,0xa61f0000,0xab64a9a8,
0x29a82c00,0xa9a80000,0xa9a8ac00,0x29a80000,0x261f2c00,0xab64a9a8,0x2b640000,0xa61f29a8,0x2c00,0xac00,0x2c00,0xac00,
0xa61f2c00,0x2b64a9a8,0xab640000,0x261f29a8,0xa9a82c00,0x29a80000,0x29a8ac00,0xa9a80000,0xab642c00,0xa61f29a8,0x261f0000,0x2b64a9a8,
0,0,0,0,0x261f0000,0x2b64a9a8,0x2b64ac00,0x261fa9a8,0x29a80000,0x29a8ac00,0xa9a80000,0xa9a82c00,
0x2b640000,0xa61fa9a8,0xa61f2c00,0x2b64a9a8,0x2c000000,0xac000000,0x2c000000,0xac000000,0x2b640000,0xa61f29a8,0xa61fac00,0x2b6429a8,
0x29a80000,0x29a82c00,0xa9a80000,0xa9a8ac00,0x261f0000,0x2b6429a8,0x2b642c00,0x261f29a8,0xac002c00,0xac002c00,0xac002c00,0xac002c00,
0xab642c00,0xa61f29a8,0x261f0000,0x2b64a9a8,0xa9a82c00,0x29a80000,0x29a8ac00,0xa9a80000,0xa61f2c00,0x2b64a9a8,0xab640000,0x261f29a8,
0x2c00,0xac00,0x2c00,0xac00,0x261f2c00,0xab64a9a8,0x2b640000,0xa61f29a8,0x29a82c00,0xa9a80000,0xa9a8ac00,0x29a80000,
0x2b642c00,0x261f29a8,0xa61f0000,0xab64a9a8,0x2c002c00,0x2c002c00,0x2c002c00,0x2c002c00,0xab64ac00,0xa61fa9a8,0x261f0000,0x2b6429a8,
0x29a82c00,0xa9a80000,0xa9a8ac00,0x29a80000,0xa61fac00,0x2b6429a8,0xab640000,0x261fa9a8,0x2c00,0xac00,0x2c00,0xac00,
0x261fac00,0xab6429a8,0x2b640000,0xa61fa9a8,0xa9a82c00,0x29a80000,0x29a8ac00,0xa9a80000,0x2b64ac00,0x261fa9a8,0xa61f0000,0xab6429a8,
0,0,0,0,0xa61f0000,0xab64a9a8,0xab64ac00,0xa61fa9a8,0x29a80000,0x29a82c00,0xa9a80000,0xa9a8ac00,
0xab640000,0x261fa9a8,0x261f2c00,0xab64a9a8,0x2c000000,0xac000000,0x2c000000,0xac000000,0xab640000,0x261f29a8,0x261fac00,0xab6429a8,
0x29a80000,0x29a8ac00,0xa9a80000,0xa9a82c00,0xa61f0000,0xab6429a8,0xab642c00,0xa61f29a8,0xac002c00,0xac002c00,0xac002c00,0xac002c00,
0x2b64ac00,0x261fa9a8,0xa61f0000,0xab6429a8,0xa9a82c00,0x29a80000,0x29a8ac00,0xa9a80000,0x261fac00,0xab6429a8,0x2b640000,0xa61fa9a8,
0x2c00,0xac00,0x2c00,0xac00,0xa61fac00,0x2b6429a8,0xab640000,0x261fa9a8,0x29a82c00,0xa9a80000,0xa9a8ac00,0x29a80000,
0xab64ac00,0xa61fa9a8,0x261f0000,0x2b6429a8,0,0,0,0,0x261f0000,0x2b64a9a8,0x2b64ac00,0x261fa9a8,
0xa9a80000,0xa9a82c00,0x29a80000,0x29a8ac00,0x2b640000,0xa61fa9a8,0xa61f2c00,0x2b64a9a8,0xac000000,0x2c000000,0xac000000,0x2c000000,
0x2b640000,0xa61f29a8,0xa61fac00,0x2b6429a8,0xa9a80000,0xa9a8ac00,0x29a80000,0x29a82c00,0x261f0000,0x2b6429a8,0x2b642c00,0x261f29a8,
0,0,0,0,0x261f0000,0x2b6429a8,0x2b642c00,0x261f29a8,0xa9a80000,0xa9a8ac00,0x29a80000,0x29a82c00,
0x2b640000,0xa61f29a8,0xa61fac00,0x2b6429a8,0xac000000,0x2c000000,0xac000000,0x2c000000,0x2b640000,0xa61fa9a8,0xa61f2c00,0x2b64a9a8,
0xa9a80000,0xa9a82c00,0x29a80000,0x29a8ac00,0x261f0000,0x2b64a9a8,0x2b64ac00,0x261fa9a8,0x2c002c00,0x2c002c00,0x2c002c00,0x2c002c00,
0xab64ac00,0xa61fa9a8,0x261f0000,0x2b6429a8,0x29a82c00,0xa9a80000,0xa9a8ac00,0x29a80000,0xa61fac00,0x2b6429a8,0xab640000,0x261fa9a8,
0x2c00,0xac00,0x2c00,0xac00,0x261fac00,0xab6429a8,0x2b640000,0xa61fa9a8,0xa9a82c00,0x29a80000,0x29a8ac00,0xa9a80000,
0x2b64ac00,0x261fa9a8,0xa61f0000,0xab6429a8,0,0,0,0,0xa61f0000,0xab6429a8,0xab642c00,0xa61f29a8,
0x29a80000,0x29a8ac00,0xa9a80000,0xa9a82c00,0xab640000,0x261f29a8,0x261fac00,0xab6429a8,0x2c000000,0xac000000,0x2c000000,0xac000000,
0xab640000,0x261fa9a8,0x261f2c00,0xab64a9a8,0x29a80000,0x29a82c00,0xa9a80000,0xa9a8ac00,0xa61f0000,0xab64a9a8,0xab64ac00,0xa61fa9a8,
0xac002c00,0xac002c00,0xac002c00,0xac002c00,0x2b64ac00,0x261fa9a8,0xa61f0000,0xab6429a8,0xa9a82c00,0x29a80000,0x29a8ac00,0xa9a80000,
0x261fac00,0xab6429a8,0x2b640000,0xa61fa9a8,0x2c00,0xac00,0x2c00,0xac00,0xa61fac00,0x2b6429a8,0xab640000,0x261fa9a8,
0x29a82c00,0xa9a80000,0xa9a8ac00,0x29a80000,0xab64ac00,0xa61fa9a8,0x261f0000,0x2b6429a8,0x2bd92c00,0x2aa72b64,0x287229a8,0x223e261f,
0x2aa72c00,0xa23e261f,0xabd9a9a8,0xa872ab64,0x28722c00,0xabd9a61f,0x223ea9a8,0x2aa72b64,0x223e2c00,0xa872ab64,0x2aa729a8,0xabd9a61f,
0xa23e2c00,0x2872ab64,0xaaa729a8,0x2bd9a61f,0xa8722c00,0x2bd9a61f,0xa23ea9a8,0xaaa72b64,0xaaa72c00,0x223e261f,0x2bd9a9a8,0x2872ab64,
0xabd92c00,0xaaa72b64,0xa87229a8,0xa23e261f,0x223e0000,0x2872261f,0x2aa729a8,0x2bd92b64,0x28720000,0x2bd92b64,0x223e29a8,0xaaa7a61f,
0x2aa70000,0x223e2b64,0xabd9a9a8,0x2872a61f,0x2bd90000,0xaaa7261f,0x2872a9a8,0xa23e2b64,0x2bd90000,0xaaa7a61f,0x287229a8,0xa23eab64,
0x2aa70000,0x223eab64,0xabd929a8,0x2872261f,0x28720000,0x2bd9ab64,0x223ea9a8,0xaaa7261f,0x223e0000,0x2872a61f,0x2aa7a9a8,0x2bd9ab64,
0xabd92c00,0xaaa72b64,0xa87229a8,0xa23e261f,0xaaa72c00,0x223e261f,0x2bd9a9a8,0x2872ab64,0xa8722c00,0x2bd9a61f,0xa23ea9a8,0xaaa72b64,
0xa23e2c00,0x2872ab64,0xaaa729a8,0x2bd9a61f,0x223e2c00,0xa872ab64,0x2aa729a8,0xabd9a61f,0x28722c00,0xabd9a61f,0x223ea9a8,0x2aa72b64,
0x2aa72c00,0xa23e261f,0xabd9a9a8,0xa872ab64,0x2bd92c00,0x2aa72b64,0x287229a8,0x223e261f,0xa23e0000,0xa872261f,0xaaa729a8,0xabd92b64,
0xa8720000,0xabd92b64,0xa23e29a8,0x2aa7a61f,0xaaa70000,0xa23e2b64,0x2bd9a9a8,0xa872a61f,0xabd90000,0x2aa7261f,0xa872a9a8,0x223e2b64,
0xabd90000,0x2aa7a61f,0xa87229a8,0x223eab64,0xaaa70000,0xa23eab64,0x2bd929a8,0xa872261f,0xa8720000,0xabd9ab64,0xa23ea9a8,0x2aa7261f,
0xa23e0000,0xa872a61f,0xaaa7a9a8,0xabd9ab64,0xa23e0000,0xa872a61f,0xaaa7a9a8,0xabd9ab64,0xa8720000,0xabd9ab64,0xa23ea9a8,0x2aa7261f,
0xaaa70000,0xa23eab64,0x2bd929a8,0xa872261f,0xabd90000,0x2aa7a61f,0xa87229a8,0x223eab64,0xabd90000,0x2aa7261f,0xa872a9a8,0x223e2b64,
0xaaa70000,0xa23e2b64,0x2bd9a9a8,0xa872a61f,0xa8720000,0xabd92b64,0xa23e29a8,0x2aa7a61f,0xa23e0000,0xa872261f,0xaaa729a8,0xabd92b64,
0x2bd92c00,0x2aa72b64,0x287229a8,0x223e261f,0x2aa72c00,0xa23e261f,0xabd9a9a8,0xa872ab64,0x28722c00,0xabd9a61f,0x223ea9a8,0x2aa72b64,
0x223e2c00,0xa872ab64,0x2aa729a8,0xabd9a61f,0xa23e2c00,0x2872ab64,0xaaa729a8,0x2bd9a61f,0xa8722c00,0x2bd9a61f,0xa23ea9a8,0xaaa72b64,
0xaaa72c00,0x223e261f,0x2bd9a9a8,0x2872ab64,0xabd92c00,0xaaa72b64,0xa87229a8,0xa23e261f,0x223e0000,0x2872a61f,0x2aa7a9a8,0x2bd9ab64,
0x28720000,0x2bd9ab64,0x223ea9a8,0xaaa7261f,0x2aa70000,0x223eab64,0xabd929a8,0x2872261f,0x2bd90000,0xaaa7a61f,0x287229a8,0xa23eab64,
0x2bd90000,0xaaa7261f,0x2872a9a8,0xa23e2b64,0x2aa70000,0x223e2b64,0xabd9a9a8,0x2872a61f,0x28720000,0x2bd92b64,0x223e29a8,0xaaa7a61f,
0x223e0000,0x2872261f,0x2aa729a8,0x2bd92b64,0xabd92c00,0xaaa72b64,0xa87229a8,0xa23e261f,0xaaa72c00,0x223e261f,0x2bd9a9a8,0x2872ab64,
0xa8722c00,0x2bd9a61f,0xa23ea9a8,0xaaa72b64,0xa23e2c00,0x2872ab64,0xaaa729a8,0x2bd9a61f,0x223e2c00,0xa872ab64,0x2aa729a8,0xabd9a61f,
0x28722c00,0xabd9a61f,0x223ea9a8,0x2aa72b64,0x2aa72c00,0xa23e261f,0xabd9a9a8,0xa872ab64,0x2bd92c00,0x2aa72b64,0x287229a8,0x223e261f,
0xa23e0000,0xa872a61f,0xaaa7a9a8,0xabd9ab64,0x28720000,0x2bd92b64,0x223e29a8,0xaaa7a61f,0xaaa70000,0xa23eab64,0x2bd929a8,0xa872261f,
0x2bd90000,0xaaa7261f,0x2872a9a8,0xa23e2b64,0xabd90000,0x2aa7261f,0xa872a9a8,0x223e2b64,0x2aa70000,0x223eab64,0xabd929a8,0x2872261f,
0xa8720000,0xabd92b64,0xa23e29a8,0x2aa7a61f,0x223e0000,0x2872a61f,0x2aa7a9a8,0x2bd9ab64,0x2bd92c00,0x2aa72b64,0x287229a8,0x223e261f,
0xaaa7ac00,0x223ea61f,0x2bd929a8,0x28722b64,0x28722c00,0xabd9a61f,0x223ea9a8,0x2aa72b64,0xa23eac00,0x28722b64,0xaaa7a9a8,0x2bd9261f,
0xa23e2c00,0x2872ab64,0xaaa729a8,0x2bd9a61f,0x2872ac00,0xabd9261f,0x223e29a8,0x2aa7ab64,0xaaa72c00,0x223e261f,0x2bd9a9a8,0x2872ab64,
0x2bd9ac00,0x2aa7ab64,0x2872a9a8,0x223ea61f,0x223e0000,0x2872a61f,0x2aa7a9a8,0x2bd9ab64,0xa8720000,0xabd92b64,0xa23e29a8,0x2aa7a61f,
0x2aa70000,0x223eab64,0xabd929a8,0x2872261f,0xabd90000,0x2aa7261f,0xa872a9a8,0x223e2b64,0x2bd90000,0xaaa7261f,0x2872a9a8,0xa23e2b64,
0xaaa70000,0xa23eab64,0x2bd929a8,0xa872261f,0x28720000,0x2bd92b64,0x223e29a8,0xaaa7a61f,0xa23e0000,0xa872a61f,0xaaa7a9a8,0xabd9ab64,
0xabd92c00,0xaaa72b64,0xa87229a8,0xa23e261f,0x2aa7ac00,0xa23ea61f,0xabd929a8,0xa8722b64,0xa8722c00,0x2bd9a61f,0xa23ea9a8,0xaaa72b64,
0x223eac00,0xa8722b64,0x2aa7a9a8,0xabd9261f,0x223e2c00,0xa872ab64,0x2aa729a8,0xabd9a61f,0xa872ac00,0x2bd9261f,0xa23e29a8,0xaaa7ab64,
0x2aa72c00,0xa23e261f,0xabd9a9a8,0xa872ab64,0xabd9ac00,0xaaa7ab64,0xa872a9a8,0xa23ea61f,0xabd9ac00,0xaaa7ab64,0xa872a9a8,0xa23ea61f,
0x2aa72c00,0xa23e261f,0xabd9a9a8,0xa872ab64,0xa872ac00,0x2bd9261f,0xa23e29a8,0xaaa7ab64,0x223e2c00,0xa872ab64,0x2aa729a8,0xabd9a61f,
0x223eac00,0xa8722b64,0x2aa7a9a8,0xabd9261f,0xa8722c00,0x2bd9a61f,0xa23ea9a8,0xaaa72b64,0x2aa7ac00,0xa23ea61f,0xabd929a8,0xa8722b64,
0xabd92c00,0xaaa72b64,0xa87229a8,0xa23e261f,0xa23e0000,0xa872a61f,0xaaa7a9a8,0xabd9ab64,0x28720000,0x2bd92b64,0x223e29a8,0xaaa7a61f,
0xaaa70000,0xa23eab64,0x2bd929a8,0xa872261f,0x2bd90000,0xaaa7261f,0x2872a9a8,0xa23e2b64,0xabd90000,0x2aa7261f,0xa872a9a8,0x223e2b64,
0x2aa70000,0x223eab64,0xabd929a8,0x2872261f,0xa8720000,0xabd92b64,0xa23e29a8,0x2aa7a61f,0x223e0000,0x2872a61f,0x2aa7a9a8,0x2bd9ab64,
0x2bd9ac00,0x2aa7ab64,0x2872a9a8,0x223ea61f,0xaaa72c00,0x223e261f,0x2bd9a9a8,0x2872ab64,0x2872ac00,0xabd9261f,0x223e29a8,0x2aa7ab64,
0xa23e2c00,0x2872ab64,0xaaa729a8,0x2bd9a61f,0xa23eac00,0x28722b64,0xaaa7a9a8,0x2bd9261f,0x28722c00,0xabd9a61f,0x223ea9a8,0x2aa72b64,
0xaaa7ac00,0x223ea61f,0x2bd929a8,0x28722b64,0x2bd92c00,0x2aa72b64,0x287229a8,0x223e261f,0x223e0000,0x2872a61f,0x2aa7a9a8,0x2bd9ab64,
0xa8720000,0xabd92b64,0xa23e29a8,0x2aa7a61f,0x2aa70000,0x223eab64,0xabd929a8,0x2872261f,0xabd90000,0x2aa7261f,0xa872a9a8,0x223e2b64,
0x2bd90000,0xaaa7261f,0x2872a9a8,0xa23e2b64,0xaaa70000,0xa23eab64,0x2bd929a8,0xa872261f,0x28720000,0x2bd92b64,0x223e29a8,0xaaa7a61f,
0xa23e0000,0xa872a61f,0xaaa7a9a8,0xabd9ab64,0x27fe2800,0x96480000,0x273b2764,0xa2d7a21f,0x27ea27f6,0x9cb29a46,0x26dd270e,0xa41da38b,
0x27c327d9,0x9fc69e3e,0x266d26a7,0xa4c4a472,0x278827a8,0xa164a0a5,0x25ed262f,0xa55fa513,0x27c32800,0x9fc60000,0xa4c4a21f,0xa66da764,
0x25ed270e,0xa55fa38b,0xa73ba62f,0xa2d7a513,0x21642472,0xa788a6a7,0xa7fea7d9,0x16489e3e,0x9cb21a46,0xa7eaa7f6,0xa6dda7a8,0x241d20a5,
0x273b2800,0xa2d70000,0xa55fa764,0x25ed221f,0x1fc62513,0xa7c3a62f,0x1cb2a0a5,0x27ea27a8,0xa4c49e3e,0xa66da7d9,0x26dd2472,0x241d26a7,
0xa7fea70e,0x9648a38b,0x278827f6,0xa1641a46,0x266d2800,0xa4c40000,0x26dd221f,0x241d2764,0xa16420a5,0xa788a7a8,0x25ed27f6,0xa55f9a46,
0xa7fea6a7,0x1648a472,0xa2d71e3e,0xa73ba7d9,0x9fc6a62f,0x27c32513,0xa7eaa70e,0x1cb2a38b,0x255f2800,0xa5ed0000,0x21642764,0xa788a21f,
0xa66d9a46,0xa4c4a7f6,0xa7c3a38b,0x9fc6a70e,0xa41da7d9,0x26dd1e3e,0x9cb2a6a7,0x27ea2472,0x273b20a5,0x22d727a8,0x27fe2513,0x1648262f,
0x241d2800,0xa6dd0000,0xa7eaa21f,0x9cb2a764,0xa7fea38b,0x9648a70e,0x2164a513,0x2788262f,0x22d7a472,0x273b26a7,0x255f27d9,0xa5ed1e3e,
0x24c427f6,0xa66d1a46,0xa7c3a0a5,0x9fc6a7a8,0x21642800,0xa7880000,0x1648a764,0x27fe221f,0xa6dda62f,0x241da513,0x24c427a8,0xa66d20a5,
0x27ea1e3e,0x1cb227d9,0xa7c3a472,0x1fc6a6a7,0xa55f238b,0xa5eda70e,0x273b9a46,0x22d727f6,0x1cb22800,0xa7ea0000,0x27c3221f,0x9fc62764,
0xa2d7a7a8,0x273ba0a5,0xa7fe9a46,0x9648a7f6,0x255f26a7,0xa5ed2472,0x27889e3e,0x216427d9,0xa6dda513,0x241da62f,0xa66d238b,0xa4c4a70e,
0x96482800,0xa7fe0000,0xa2d72764,0xa73ba21f,0x1cb2a7f6,0x27ea1a46,0x241da70e,0x26dd238b,0x9fc627d9,0xa7c39e3e,0xa4c426a7,0xa66da472,
0x2164a7a8,0x278820a5,0x255fa62f,0x25ed2513,0x9fc62800,0xa7c30000,0xa66da21f,0x24c4a764,0x255fa70e,0x25ed238b,0x22d7262f,0xa73b2513,
0xa7882472,0xa164a6a7,0x1648a7d9,0x27fe9e3e,0x27ea9a46,0x9cb227f6,0xa41d27a8,0xa6dda0a5,0xa2d72800,0xa73b0000,0x25eda764,0x255f221f,
0x27c3a513,0x1fc6262f,0xa7ea20a5,0x1cb2a7a8,0xa66d9e3e,0x24c4a7d9,0x241d2472,0xa6dd26a7,0x1648270e,0xa7fe238b,0x2164a7f6,0x27889a46,
0xa4c42800,0xa66d0000,0x241d221f,0xa6dd2764,0x2788a0a5,0xa16427a8,0x255fa7f6,0x25ed1a46,0x1648a6a7,0x27fea472,0xa73b1e3e,0x22d7a7d9,
0xa7c3262f,0x9fc6a513,0x9cb2270e,0xa7ea238b,0xa5ed2800,0xa55f0000,0xa7882764,0xa164a21f,0x24c41a46,0xa66d27f6,0x1fc6238b,0xa7c3270e,
0x26dda7d9,0x241d1e3e,0x27eaa6a7,0x1cb22472,0xa2d7a0a5,0x273ba7a8,0x9648a513,0x27fea62f,0xa6dd2800,0xa41d0000,0x9cb2a21f,0x27eaa764,
0x1648238b,0xa7fe270e,0xa7882513,0x2164a62f,0x273ba472,0xa2d726a7,0xa5ed27d9,0xa55f1e3e,0x266da7f6,0x24c49a46,0x1fc620a5,0xa7c327a8,
0xa7882800,0xa1640000,0x27fea764,0x9648221f,0xa41d262f,0xa6dd2513,0x266da7a8,0x24c4a0a5,0x1cb21e3e,0xa7ea27d9,0x1fc6a472,0x27c3a6a7,
0x25eda38b,0xa55f270e,0xa2d71a46,0x273ba7f6,0xa7ea2800,0x9cb20000,0x9fc6221f,0xa7c32764,0xa73b27a8,0xa2d720a5,0x16481a46,0xa7fe27f6,
0xa5ed26a7,0xa55f2472,0x21649e3e,0xa78827d9,0xa41d2513,0xa6dd262f,0x24c4a38b,0xa66d270e,0xa7fe2800,0x16480000,0xa73b2764,0x22d7a21f,
0xa7ea27f6,0x1cb29a46,0xa6dd270e,0x241da38b,0xa7c327d9,0x1fc69e3e,0xa66d26a7,0x24c4a472,0xa78827a8,0x2164a0a5,0xa5ed262f,0x255fa513,
0xa7c32800,0x1fc60000,0x24c4a21f,0x266da764,0xa5ed270e,0x255fa38b,0x273ba62f,0x22d7a513,0xa1642472,0x2788a6a7,0x27fea7d9,0x96489e3e,
0x1cb21a46,0x27eaa7f6,0x26dda7a8,0xa41d20a5,0xa73b2800,0x22d70000,0x255fa764,0xa5ed221f,0x9fc62513,0x27c3a62f,0x9cb2a0a5,0xa7ea27a8,
0x24c49e3e,0x266da7d9,0xa6dd2472,0xa41d26a7,0x27fea70e,0x1648a38b,0xa78827f6,0x21641a46,0xa66d2800,0x24c40000,0xa6dd221f,0xa41d2764,
0x216420a5,0x2788a7a8,0xa5ed27f6,0x255f9a46,0x27fea6a7,0x9648a472,0x22d71e3e,0x273ba7d9,0x1fc6a62f,0xa7c32513,0x27eaa70e,0x9cb2a38b,
0xa55f2800,0x25ed0000,0xa1642764,0x2788a21f,0x266d9a46,0x24c4a7f6,0x27c3a38b,0x1fc6a70e,0x241da7d9,0xa6dd1e3e,0x1cb2a6a7,0xa7ea2472,
0xa73b20a5,0xa2d727a8,0xa7fe2513,0x9648262f,0xa41d2800,0x26dd0000,0x27eaa21f,0x1cb2a764,0x27fea38b,0x1648a70e,0xa164a513,0xa788262f,
0xa2d7a472,0xa73b26a7,0xa55f27d9,0x25ed1e3e,0xa4c427f6,0x266d1a46,0x27c3a0a5,0x1fc6a7a8,0xa1642800,0x27880000,0x9648a764,0xa7fe221f,
0x26dda62f,0xa41da513,0xa4c427a8,0x266d20a5,0xa7ea1e3e,0x9cb227d9,0x27c3a472,0x9fc6a6a7,0x255f238b,0x25eda70e,0xa73b9a46,0xa2d727f6,
0x9cb22800,0x27ea0000,0xa7c3221f,0x1fc62764,0x22d7a7a8,0xa73ba0a5,0x27fe9a46,0x1648a7f6,0xa55f26a7,0x25ed2472,0xa7889e3e,0xa16427d9,
0x26dda513,0xa41da62f,0x266d238b,0x24c4a70e,0x16482800,0x27fe0000,0x22d72764,0x273ba21f,0x9cb2a7f6,0xa7ea1a46,0xa41da70e,0xa6dd238b,
0x1fc627d9,0x27c39e3e,0x24c426a7,0x266da472,0xa164a7a8,0xa78820a5,0xa55fa62f,0xa5ed2513,0x1fc62800,0x27c30000,0x266da21f,0xa4c4a764,
0xa55fa70e,0xa5ed238b,0xa2d7262f,0x273b2513,0x27882472,0x2164a6a7,0x9648a7d9,0xa7fe9e3e,0xa7ea9a46,0x1cb227f6,0x241d27a8,0x26dda0a5,
0x22d72800,0x273b0000,0xa5eda764,0xa55f221f,0xa7c3a513,0x9fc6262f,0x27ea20a5,0x9cb2a7a8,0x266d9e3e,0xa4c4a7d9,0xa41d2472,0x26dd26a7,
0x9648270e,0x27fe238b,0xa164a7f6,0xa7889a46,0x24c42800,0x266d0000,0xa41d221f,0x26dd2764,0xa788a0a5,0x216427a8,0xa55fa7f6,0xa5ed1a46,
0x9648a6a7,0xa7fea472,0x273b1e3e,0xa2d7a7d9,0x27c3262f,0x1fc6a513,0x1cb2270e,0x27ea238b,0x25ed2800,0x255f0000,0x27882764,0x2164a21f,
0xa4c41a46,0x266d27f6,0x9fc6238b,0x27c3270e,0xa6dda7d9,0xa41d1e3e,0xa7eaa6a7,0x9cb22472,0x22d7a0a5,0xa73ba7a8,0x1648a513,0xa7fea62f,
0x26dd2800,0x241d0000,0x1cb2a21f,0xa7eaa764,0x9648238b,0x27fe270e,0x27882513,0xa164a62f,0xa73ba472,0x22d726a7,0x25ed27d9,0x255f1e3e,
0xa66da7f6,0xa4c49a46,0x9fc620a5,0x27c327a8,0x27882800,0x21640000,0xa7fea764,0x1648221f,0x241d262f,0x26dd2513,0xa66da7a8,0xa4c4a0a5,
0x9cb21e3e,0x27ea27d9,0x9fc6a472,0xa7c3a6a7,0xa5eda38b,0x255f270e,0x22d71a46,0xa73ba7f6,0x27ea2800,0x1cb20000,0x1fc6221f,0x27c32764,
0x273b27a8,0x22d720a5,0x96481a46,0x27fe27f6,0x25ed26a7,0x255f2472,0xa1649e3e,0x278827d9,0x241d2513,0x26dd262f,0xa4c4a38b,0x266d270e,
0x255f25a8,0xa5eda5a8,0x2164221f,0xa788a764,0x24c42513,0xa66da62f,0x1fc620a5,0xa7c3a7a8,0x241d2472,0xa6dda6a7,0x1cb21e3e,0xa7eaa7d9,
0x22d7238b,0xa73ba70e,0x16481a46,0xa7fea7f6,0xa41da5a8,0x26dd25a8,0x27ea2764,0x1cb2221f,0x9648a0a5,0x27fe27a8,0x278827f6,0xa1649a46,
0x22d71e3e,0x273b27d9,0x255f26a7,0xa5eda472,0x266d2513,0x24c4262f,0x1fc6238b,0xa7c3a70e,0x216425a8,0xa788a5a8,0x1648a21f,0x27fe2764,
0xa41d9a46,0xa6dda7f6,0x266d238b,0x24c4270e,0xa7eaa6a7,0x9cb2a472,0x27c327d9,0x9fc61e3e,0xa5eda7a8,0x255f20a5,0x22d7262f,0xa73ba513,
0x9cb2a5a8,0x27ea25a8,0xa7c3a764,0x1fc6a21f,0x273b238b,0x22d7270e,0x9648a513,0x27fe262f,0x255f27d9,0xa5ed9e3e,0x27882472,0x216426a7,
0xa41d1a46,0xa6dda7f6,0x24c427a8,0xa66da0a5,0x964825a8,0xa7fea5a8,0xa2d7221f,0xa73ba764,0xa7eaa62f,0x1cb2a513,0xa6dda7a8,0x241da0a5,
0x1fc6a472,0x27c326a7,0x24c49e3e,0x266d27d9,0x2788270e,0xa164238b,0x25ed27f6,0xa55f1a46,0x1fc6a5a8,0x27c325a8,0x266d2764,0xa4c4221f,
0x25ed27a8,0xa55f20a5,0xa73b9a46,0xa2d7a7f6,0xa7889e3e,0xa164a7d9,0x1648a6a7,0x27fe2472,0x1cb2a62f,0x27ea2513,0x26dd270e,0xa41d238b,
0xa2d725a8,0xa73ba5a8,0x25eda21f,0x255f2764,0x9fc6a7f6,0x27c31a46,0x9cb2270e,0xa7eaa38b,0x266d26a7,0xa4c42472,0xa41da7d9,0x26dd9e3e,
0xa7fea0a5,0x9648a7a8,0x27882513,0xa164262f,0x24c4a5a8,0x266d25a8,0xa41da764,0x26dda21f,0xa164270e,0xa788a38b,0x25ed262f,0xa55f2513,
0x1648a7d9,0x27fe1e3e,0xa73ba472,0x22d7a6a7,0x1fc627f6,0xa7c31a46,0x27ea20a5,0x9cb227a8,0xa5ed25a8,0xa55fa5a8,0xa788221f,0xa164a764,
0x266da513,0x24c4262f,0x27c3a0a5,0x1fc627a8,0xa6dd2472,0xa41da6a7,0xa7ea1e3e,0x9cb2a7d9,0x273ba38b,0x22d7270e,0x27fe9a46,0x164827f6,
0x26dda5a8,0x241d25a8,0x1cb22764,0xa7ea221f,0xa7fe20a5,0x9648a7a8,0x2164a7f6,0x27881a46,0x273b1e3e,0xa2d727d9,0xa5ed26a7,0xa55fa472,
0xa4c4a513,0x266da62f,0x27c3a38b,0x1fc6270e,0xa78825a8,0xa164a5a8,0x27fea21f,0x96482764,0x26dd1a46,0xa41d27f6,0xa4c4a38b,0x266da70e,
0x9cb2a6a7,0x27eaa472,0x9fc627d9,0xa7c31e3e,0xa55f27a8,0xa5eda0a5,0x273ba62f,0x22d72513,0x27eaa5a8,0x1cb225a8,0x1fc6a764,0x27c3a21f,
0xa2d7a38b,0x273ba70e,0xa7fe2513,0x9648a62f,0xa5ed27d9,0xa55f9e3e,0x21642472,0xa78826a7,0x26dd9a46,0xa41d27f6,0x266da7a8,0x24c420a5,
0xa7fe25a8,0x1648a5a8,0xa73b221f,0x22d7a764,0x9cb2262f,0xa7ea2513,0xa41d27a8,0xa6dd20a5,0x27c3a472,0x9fc626a7,0x266d9e3e,0xa4c427d9,
0x2164a70e,0x2788a38b,0x255fa7f6,0x25ed9a46,0x27c3a5a8,0x9fc625a8,0xa4c42764,0xa66d221f,0x255fa7a8,0x25eda0a5,0x22d71a46,0xa73b27f6,
0xa1649e3e,0x2788a7d9,0x27fea6a7,0x96482472,0xa7ea262f,0x1cb2a513,0x241da70e,0x26dda38b,0xa73b25a8,0x22d7a5a8,0x255fa21f,0xa5ed2764,
0xa7c327f6,0x9fc69a46,0x27eaa70e,0x9cb2238b,0xa4c426a7,0xa66d2472,0x26dda7d9,0x241d9e3e,0x164820a5,0xa7fe27a8,0x2164a513,0x2788a62f,
0x266da5a8,0xa4c425a8,0x26dda764,0x241da21f,0x2788a70e,0xa164238b,0x255fa62f,0x25eda513,0x27fea7d9,0x96481e3e,0x22d7a472,0x273ba6a7,
0x27c3a7f6,0x1fc69a46,0x1cb2a0a5,0x27eaa7a8,0xa55f25a8,0x25eda5a8,0xa164221f,0x2788a764,0xa4c42513,0x266da62f,0x9fc620a5,0x27c3a7a8,
0xa41d2472,0x26dda6a7,0x9cb21e3e,0x27eaa7d9,0xa2d7238b,0x273ba70e,0x96481a46,0x27fea7f6,0x241da5a8,0xa6dd25a8,0xa7ea2764,0x9cb2221f,
0x1648a0a5,0xa7fe27a8,0xa78827f6,0x21649a46,0xa2d71e3e,0xa73b27d9,0xa55f26a7,0x25eda472,0xa66d2513,0xa4c4262f,0x9fc6238b,0x27c3a70e,
0xa16425a8,0x2788a5a8,0x9648a21f,0xa7fe2764,0x241d9a46,0x26dda7f6,0xa66d238b,0xa4c4270e,0x27eaa6a7,0x1cb2a472,0xa7c327d9,0x1fc61e3e,
0x25eda7a8,0xa55f20a5,0xa2d7262f,0x273ba513,0x1cb2a5a8,0xa7ea25a8,0x27c3a764,0x9fc6a21f,0xa73b238b,0xa2d7270e,0x1648a513,0xa7fe262f,
0xa55f27d9,0x25ed9e3e,0xa7882472,0xa16426a7,0x241d1a46,0x26dda7f6,0xa4c427a8,0x266da0a5,0x164825a8,0x27fea5a8,0x22d7221f,0x273ba764,
0x27eaa62f,0x9cb2a513,0x26dda7a8,0xa41da0a5,0x9fc6a472,0xa7c326a7,0xa4c49e3e,0xa66d27d9,0xa788270e,0x2164238b,0xa5ed27f6,0x255f1a46,
0x9fc6a5a8,0xa7c325a8,0xa66d2764,0x24c4221f,0xa5ed27a8,0x255f20a5,0x273b9a46,0x22d7a7f6,0x27889e3e,0x2164a7d9,0x9648a6a7,0xa7fe2472,
0x9cb2a62f,0xa7ea2513,0xa6dd270e,0x241d238b,0x22d725a8,0x273ba5a8,0xa5eda21f,0xa55f2764,0x1fc6a7f6,0xa7c31a46,0x1cb2270e,0x27eaa38b,
0xa66d26a7,0x24c42472,0x241da7d9,0xa6dd9e3e,0x27fea0a5,0x1648a7a8,0xa7882513,0x2164262f,0xa4c4a5a8,0xa66d25a8,0x241da764,0xa6dda21f,
0x2164270e,0x2788a38b,0xa5ed262f,0x255f2513,0x9648a7d9,0xa7fe1e3e,0x273ba472,0xa2d7a6a7,0x9fc627f6,0x27c31a46,0xa7ea20a5,0x1cb227a8,
0x25ed25a8,0x255fa5a8,0x2788221f,0x2164a764,0xa66da513,0xa4c4262f,0xa7c3a0a5,0x9fc627a8,0x26dd2472,0x241da6a7,0x27ea1e3e,0x1cb2a7d9,
0xa73ba38b,0xa2d7270e,0xa7fe9a46,0x964827f6,0xa6dda5a8,0xa41d25a8,0x9cb22764,0x27ea221f,0x27fe20a5,0x1648a7a8,0xa164a7f6,0xa7881a46,
0xa73b1e3e,0x22d727d9,0x25ed26a7,0x255fa472,0x24c4a513,0xa66da62f,0xa7c3a38b,0x9fc6270e,0x278825a8,0x2164a5a8,0xa7fea21f,0x16482764,
0xa6dd1a46,0x241d27f6,0x24c4a38b,0xa66da70e,0x1cb2a6a7,0xa7eaa472,0x1fc627d9,0x27c31e3e,0x255f27a8,0x25eda0a5,0xa73ba62f,0xa2d72513,
0xa7eaa5a8,0x9cb225a8,0x9fc6a764,0xa7c3a21f,0x22d7a38b,0xa73ba70e,0x27fe2513,0x1648a62f,0x25ed27d9,0x255f9e3e,0xa1642472,0x278826a7,
0xa6dd9a46,0x241d27f6,0xa66da7a8,0xa4c420a5,0x27fe25a8,0x9648a5a8,0x273b221f,0xa2d7a764,0x1cb2262f,0x27ea2513,0x241d27a8,0x26dd20a5,
0xa7c3a472,0x1fc626a7,0xa66d9e3e,0x24c427d9,0xa164a70e,0xa788a38b,0xa55fa7f6,0xa5ed9a46,0xa7c3a5a8,0x1fc625a8,0x24c42764,0x266d221f,
0xa55fa7a8,0xa5eda0a5,0xa2d71a46,0x273b27f6,0x21649e3e,0xa788a7d9,0xa7fea6a7,0x16482472,0x27ea262f,0x9cb2a513,0xa41da70e,0xa6dda38b,
0x273b25a8,0xa2d7a5a8,0xa55fa21f,0x25ed2764,0x27c327f6,0x1fc69a46,0xa7eaa70e,0x1cb2238b,0x24c426a7,0x266d2472,0xa6dda7d9,0xa41d9e3e,
0x964820a5,0x27fe27a8,0xa164a513,0xa788a62f,0xa66da5a8,0x24c425a8,0xa6dda764,0xa41da21f,0xa788a70e,0x2164238b,0xa55fa62f,0xa5eda513,
0xa7fea7d9,0x16481e3e,0xa2d7a472,0xa73ba6a7,0xa7c3a7f6,0x9fc69a46,0x9cb2a0a5,0xa7eaa7a8,
};

#define PROF(slot) do {} while (0)
#define PROF3(slot) do {} while (0)
#define PROF2(slot) do {} while (0)

__device__ __forceinline__ uint32_t smem_u32(const void* p) { return (uint32_t)__cvta_generic_to_shared(p); }

__device__ __forceinline__ void mbar_init(uint32_t a, uint32_t c) {
  asm volatile("mbarrier.init.shared::cta.b64 [%0], %1;\n" ::"r"(a), "r"(c) : "memory");
}
__device__ __forceinline__ void mbar_expect_tx(uint32_t a, uint32_t bytes) {
  asm volatile("mbarrier.arrive.expect_tx.shared::cta.b64 _, [%0], %1;\n" ::"r"(a), "r"(bytes) : "memory");
}
__device__ __forceinline__ void mbar_arrive_cluster(uint32_t cluster_addr) {
  asm volatile("mbarrier.arrive.shared::cluster.b64 _, [%0];\n" ::"r"(cluster_addr) : "memory");
}
__device__ __forceinline__ void mbar_arrive_cluster_n(uint32_t cluster_addr, uint32_t n) {
  asm volatile("mbarrier.arrive.shared::cluster.b64 _, [%0], %1;\n" ::"r"(cluster_addr), "r"(n) : "memory");
}
__device__ __forceinline__ bool mbar_try(uint32_t a, uint32_t parity) {
  uint32_t ok;
  asm volatile("{\n.reg .pred p;\nmbarrier.try_wait.parity.shared::cta.b64 p, [%1], %2;\nselp.u32 %0, 1, 0, p;\n}\n"
               : "=r"(ok) : "r"(a), "r"(parity) : "memory");
  return ok;
}
__device__ __forceinline__ void mbar_wait(uint32_t a, uint32_t parity) {
  if (mbar_try(a, parity)) return;
#pragma unroll 1
  for (int n = 0; n < SPIN_LIMIT; n++)
    if (mbar_try(a, parity)) break;
}
__device__ __forceinline__ void mbar_wait_idle(uint32_t a, uint32_t parity) {
#pragma unroll 1
  for (int n = 0; n < SPIN_LIMIT; n++) {
    uint32_t ok;
    asm volatile("{\n.reg .pred p;\nmbarrier.try_wait.parity.shared::cta.b64 p, [%1], %2, %3;\nselp.u32 %0, 1, 0, p;\n}\n"
                 : "=r"(ok) : "r"(a), "r"(parity), "r"(4000) : "memory");
    if (ok) break;
  }
}
__device__ __forceinline__ bool elect_one() {
  uint32_t p;
  asm volatile("{\n.reg .pred P;\nelect.sync _|P, 0xffffffff;\nselp.u32 %0, 1, 0, P;\n}\n" : "=r"(p));
  return p;
}
__device__ __forceinline__ uint32_t mapa(uint32_t a, uint32_t rank) {
  uint32_t r;
  asm volatile("mapa.shared::cluster.u32 %0, %1, %2;\n" : "=r"(r) : "r"(a), "r"(rank));
  return r;
}
__device__ __forceinline__ void nb_sync(int id, int n) { asm volatile("bar.sync %0, %1;\n" ::"r"(id), "r"(n) : "memory"); }
__device__ __forceinline__ void nb_arrive(int id, int n) { asm volatile("bar.arrive %0, %1;\n" ::"r"(id), "r"(n) : "memory"); }
__device__ __forceinline__ void cluster_sync_all() {
  asm volatile("barrier.cluster.arrive.relaxed.aligned;\nbarrier.cluster.wait.aligned;\n" ::: "memory");
}
__device__ __forceinline__ void fence_async_smem() { asm volatile("fence.proxy.async.shared::cta;\n" ::: "memory"); }
__device__ __forceinline__ void fence_async_all() { asm volatile("fence.proxy.async.global;\n" ::: "memory"); }

__device__ __forceinline__ void tma_load_3d(uint32_t dst, const CUtensorMap* tm, uint32_t bar, int c0, int c1, int c2) {
  asm volatile(
      "cp.async.bulk.tensor.3d.shared::cluster.global.mbarrier::complete_tx::bytes [%0], [%1, {%3, %4, %5}], [%2];\n"
      ::"r"(dst), "l"(tm), "r"(bar), "r"(c0), "r"(c1), "r"(c2) : "memory");
}
__device__ __forceinline__ void tma_load_4d(uint32_t dst, const CUtensorMap* tm, uint32_t bar, int c0, int c1, int c2, int c3) {
  asm volatile(
      "cp.async.bulk.tensor.4d.shared::cluster.global.mbarrier::complete_tx::bytes [%0], [%1, {%3, %4, %5, %6}], [%2];\n"
      ::"r"(dst), "l"(tm), "r"(bar), "r"(c0), "r"(c1), "r"(c2), "r"(c3) : "memory");
}
__device__ __forceinline__ void tma_load_3d_mc(uint32_t dst, const CUtensorMap* tm, uint32_t bar, int c0, int c1, int c2) {
  asm volatile(
      "cp.async.bulk.tensor.3d.shared::cluster.global.mbarrier::complete_tx::bytes.multicast::cluster [%0], [%1, {%3, %4, %5}], [%2], %6;\n"
      ::"r"(dst), "l"(tm), "r"(bar), "r"(c0), "r"(c1), "r"(c2), "h"((uint16_t)3) : "memory");
}
__device__ __forceinline__ void tma_load_5d(uint32_t dst, const CUtensorMap* tm, uint32_t bar, int c0, int c4) {
  asm volatile(
      "cp.async.bulk.tensor.5d.shared::cluster.global.mbarrier::complete_tx::bytes [%0], [%1, {%3, %5, %5, %5, %4}], [%2];\n"
      ::"r"(dst), "l"(tm), "r"(bar), "r"(c0), "r"(c4), "r"(0) : "memory");
}
__device__ __forceinline__ void bulk_load(uint32_t dst, const void* src, uint32_t bytes, uint32_t bar) {
  asm volatile("cp.async.bulk.shared::cluster.global.mbarrier::complete_tx::bytes [%0], [%1], %2, [%3];\n"
               ::"r"(dst), "l"(src), "r"(bytes), "r"(bar) : "memory");
}
__device__ __forceinline__ void bulk_commit() { asm volatile("cp.async.bulk.commit_group;\n" ::: "memory"); }
__device__ __forceinline__ void bulk_wait0() { asm volatile("cp.async.bulk.wait_group 0;\n" ::: "memory"); }
__device__ __forceinline__ void prefetch_tmap(const CUtensorMap* tm) {
  asm volatile("prefetch.tensormap [%0];\n" ::"l"(tm) : "memory");
}

__device__ __forceinline__ void wg_fence() { asm volatile("wgmma.fence.sync.aligned;\n" ::: "memory"); }
__device__ __forceinline__ void wg_commit() { asm volatile("wgmma.commit_group.sync.aligned;\n" ::: "memory"); }
template <int N> __device__ __forceinline__ void wg_wait() {
  asm volatile("wgmma.wait_group.sync.aligned %0;\n" ::"n"(N) : "memory");
}
__device__ __forceinline__ uint64_t mkdesc(uint32_t addr, uint32_t lbo, uint32_t sbo, uint32_t swz) {
  return (uint64_t)((addr & 0x3FFFF) >> 4) | ((uint64_t)(lbo >> 4) << 16) | ((uint64_t)(sbo >> 4) << 32) |
         ((uint64_t)swz << 62);
}

#define R4(d, o) "+f"(d[o + 0]), "+f"(d[o + 1]), "+f"(d[o + 2]), "+f"(d[o + 3])
#define R8(d, o) R4(d, o), R4(d, o + 4)
#define R16(d, o) R8(d, o), R8(d, o + 8)
#define R32(d, o) R16(d, o), R16(d, o + 16)
#define R64(d, o) R32(d, o), R32(d, o + 32)

__device__ __forceinline__ void wgmma_n192(float (&d)[96], uint64_t da, uint64_t db, uint32_t acc) {
  asm volatile(
      "{\n.reg .pred p;\nsetp.ne.u32 p, %98, 0;\n"
      "wgmma.mma_async.sync.aligned.m64n192k16.f32.bf16.bf16 "
      "{%0,%1,%2,%3,%4,%5,%6,%7,%8,%9,%10,%11,%12,%13,%14,%15,%16,%17,%18,%19,%20,%21,%22,%23,%24,%25,%26,%27,%28,%29,%30,%31,"
      "%32,%33,%34,%35,%36,%37,%38,%39,%40,%41,%42,%43,%44,%45,%46,%47,%48,%49,%50,%51,%52,%53,%54,%55,%56,%57,%58,%59,%60,%61,%62,%63,"
      "%64,%65,%66,%67,%68,%69,%70,%71,%72,%73,%74,%75,%76,%77,%78,%79,%80,%81,%82,%83,%84,%85,%86,%87,%88,%89,%90,%91,%92,%93,%94,%95}, "
      "%96, %97, p, 1, 1, 0, 1;\n}\n"
      : R64(d, 0), R32(d, 64)
      : "l"(da), "l"(db), "r"(acc));
}
__device__ __forceinline__ void wgmma_n128(float (&d)[64], uint64_t da, uint64_t db, uint32_t acc) {
  asm volatile(
      "{\n.reg .pred p;\nsetp.ne.u32 p, %66, 0;\n"
      "wgmma.mma_async.sync.aligned.m64n128k16.f32.bf16.bf16 "
      "{%0,%1,%2,%3,%4,%5,%6,%7,%8,%9,%10,%11,%12,%13,%14,%15,%16,%17,%18,%19,%20,%21,%22,%23,%24,%25,%26,%27,%28,%29,%30,%31,"
      "%32,%33,%34,%35,%36,%37,%38,%39,%40,%41,%42,%43,%44,%45,%46,%47,%48,%49,%50,%51,%52,%53,%54,%55,%56,%57,%58,%59,%60,%61,%62,%63}, "
      "%64, %65, p, 1, 1, 0, 1;\n}\n"
      : R64(d, 0)
      : "l"(da), "l"(db), "r"(acc));
}
template <int N> __device__ __forceinline__ void fence_regs(float (&d)[N]) {
#pragma unroll
  for (int i = 0; i < N; i++) asm volatile("" : "+f"(d[i])::"memory");
}

__device__ __forceinline__ void mma16816(float (&d)[4], uint32_t a0, uint32_t a1, uint32_t a2, uint32_t a3, uint32_t b0,
                                         uint32_t b1) {
  asm("mma.sync.aligned.m16n8k16.row.col.f32.bf16.bf16.f32 {%0,%1,%2,%3}, {%4,%5,%6,%7}, {%8,%9}, {%0,%1,%2,%3};\n"
      : "+f"(d[0]), "+f"(d[1]), "+f"(d[2]), "+f"(d[3])
      : "r"(a0), "r"(a1), "r"(a2), "r"(a3), "r"(b0), "r"(b1));
}
__device__ __forceinline__ void mma16816_z(float (&d)[4], uint32_t a0, uint32_t a1, uint32_t a2, uint32_t a3, uint32_t b0,
                                           uint32_t b1) {
  asm("mma.sync.aligned.m16n8k16.row.col.f32.bf16.bf16.f32 {%0,%1,%2,%3}, {%4,%5,%6,%7}, {%8,%9}, {%10,%10,%10,%10};\n"
      : "=f"(d[0]), "=f"(d[1]), "=f"(d[2]), "=f"(d[3])
      : "r"(a0), "r"(a1), "r"(a2), "r"(a3), "r"(b0), "r"(b1), "f"(0.f));
}
__device__ __forceinline__ void ldsm4t(uint32_t (&r)[4], uint32_t a) {
  asm volatile("ldmatrix.sync.aligned.m8n8.x4.trans.shared.b16 {%0,%1,%2,%3}, [%4];\n"
               : "=r"(r[0]), "=r"(r[1]), "=r"(r[2]), "=r"(r[3]) : "r"(a) : "memory");
}
__device__ __forceinline__ void ldsm2t(uint32_t& r0, uint32_t& r1, uint32_t a) {
  asm volatile("ldmatrix.sync.aligned.m8n8.x2.trans.shared.b16 {%0,%1}, [%2];\n" : "=r"(r0), "=r"(r1) : "r"(a) : "memory");
}
__device__ __forceinline__ void st_async128(uint32_t a, uint32_t bar, uint32_t x, uint32_t y, uint32_t z, uint32_t w) {
  asm volatile("st.async.weak.shared::cluster.mbarrier::complete_tx::bytes.v4.b32 [%0], {%2,%3,%4,%5}, [%1];\n"
               ::"r"(a), "r"(bar), "r"(x), "r"(y), "r"(z), "r"(w) : "memory");
}
__device__ __forceinline__ void mbar_arrive(uint32_t a) {
  asm volatile("mbarrier.arrive.shared::cta.b64 _, [%0];\n" ::"r"(a) : "memory");
}
__device__ __forceinline__ void stsm4(uint32_t a, uint32_t r0, uint32_t r1, uint32_t r2, uint32_t r3) {
  asm volatile("stmatrix.sync.aligned.m8n8.x4.shared.b16 [%0], {%1,%2,%3,%4};\n"
               ::"r"(a), "r"(r0), "r"(r1), "r"(r2), "r"(r3) : "memory");
}
__device__ __forceinline__ void stsm4t(uint32_t a, uint32_t r0, uint32_t r1, uint32_t r2, uint32_t r3) {
  asm volatile("stmatrix.sync.aligned.m8n8.x4.trans.shared.b16 [%0], {%1,%2,%3,%4};\n"
               ::"r"(a), "r"(r0), "r"(r1), "r"(r2), "r"(r3) : "memory");
}
__device__ __forceinline__ uint2 lds64(uint32_t a) {
  uint2 v;
  asm volatile("ld.shared.v2.u32 {%0,%1}, [%2];\n" : "=r"(v.x), "=r"(v.y) : "r"(a));
  return v;
}
__device__ __forceinline__ uint4 lds128(uint32_t a) {
  uint4 v;
  asm volatile("ld.shared.v4.u32 {%0,%1,%2,%3}, [%4];\n" : "=r"(v.x), "=r"(v.y), "=r"(v.z), "=r"(v.w) : "r"(a) : "memory");
  return v;
}
__device__ __forceinline__ void sts128(uint32_t a, uint32_t x, uint32_t y, uint32_t z, uint32_t w) {
  asm volatile("st.shared.v4.u32 [%0], {%1,%2,%3,%4};\n" ::"r"(a), "r"(x), "r"(y), "r"(z), "r"(w) : "memory");
}
__device__ __forceinline__ uint32_t pack_bf16(float lo, float hi) {
  uint32_t r;
  asm("cvt.rn.bf16x2.f32 %0, %1, %2;\n" : "=r"(r) : "f"(hi), "f"(lo));
  return r;
}
__device__ __forceinline__ uint32_t bmul2(uint32_t a, uint32_t b) {
  uint32_t r;
  asm("mul.rn.bf16x2 %0, %1, %2;\n" : "=r"(r) : "r"(a), "r"(b));
  return r;
}
__device__ __forceinline__ uint32_t bmax2(uint32_t a, uint32_t b) {
  uint32_t r;
  asm("max.bf16x2 %0, %1, %2;\n" : "=r"(r) : "r"(a), "r"(b));
  return r;
}
__device__ __forceinline__ uint32_t bfma2(uint32_t a, uint32_t b, uint32_t c) {
  uint32_t r;
  asm("fma.rn.bf16x2 %0, %1, %2, %3;\n" : "=r"(r) : "r"(a), "r"(b), "r"(c));
  return r;
}
__device__ __forceinline__ void prefetch_l2(const void* p) { asm volatile("prefetch.global.L2 [%0];\n" ::"l"(p)); }
__device__ __forceinline__ void cp_async16n(uint32_t dst, const void* src) {
  asm volatile("cp.async.cg.shared.global [%0], [%1], 16;\n" ::"r"(dst), "l"(src) : "memory");
}
__device__ __forceinline__ void cp_async16(uint32_t dst, const void* src, uint32_t srcbytes) {
  asm volatile("cp.async.cg.shared.global.L2::256B [%0], [%1], 16, %2;\n" ::"r"(dst), "l"(src), "r"(srcbytes) : "memory");
}
__device__ __forceinline__ uint32_t ld_acquire(const uint32_t* p) {
  uint32_t v;
  asm volatile("ld.acquire.gpu.global.u32 %0, [%1];\n" : "=r"(v) : "l"(p) : "memory");
  return v;
}
__device__ __forceinline__ uint32_t ld_relaxed(const uint32_t* p) {
  uint32_t v;
  asm volatile("ld.relaxed.gpu.global.u32 %0, [%1];\n" : "=r"(v) : "l"(p) : "memory");
  return v;
}
__device__ __forceinline__ void st_release(uint32_t* p, uint32_t v) {
  asm volatile("st.release.gpu.global.u32 [%0], %1;\n" ::"l"(p), "r"(v) : "memory");
}
__device__ __forceinline__ void wait_flag(const uint32_t* p, uint32_t want) {
  int n = 0;
  while (ld_relaxed(p) != want && ++n < SPIN_LIMIT) __nanosleep(40);
  (void)ld_acquire(p);
}

struct Params {
  const __nv_bfloat16* x;
  const __nv_bfloat16* w;
  const __nv_bfloat16* q;
  const __nv_bfloat16* k;
  const __nv_bfloat16* v;
  const __nv_bfloat16* shift_k;
  const __nv_bfloat16* ssm_k;
  const __nv_bfloat16* ssm_D;
  const __nv_bfloat16* wo;
  __nv_bfloat16* out;
};

#define U4(c, d, o) c(d[o + 0]), c(d[o + 1]), c(d[o + 2]), c(d[o + 3])
#define U8(c, d, o) U4(c, d, o), U4(c, d, o + 4)
#define U16(c, d, o) U8(c, d, o), U8(c, d, o + 8)
#define U32(c, d, o) U16(c, d, o), U16(c, d, o + 16)
#define D32 "{%0,%1,%2,%3,%4,%5,%6,%7,%8,%9,%10,%11,%12,%13,%14,%15,%16,%17,%18,%19,%20,%21,%22,%23,%24,%25,%26,%27,%28,%29,%30,%31}"
#define D16 "{%0,%1,%2,%3,%4,%5,%6,%7,%8,%9,%10,%11,%12,%13,%14,%15}"
#define D8 "{%0,%1,%2,%3,%4,%5,%6,%7}"
template <int ACC> __device__ __forceinline__ void hmma_n128t(uint32_t (&d)[32], const uint32_t (&a)[4], uint64_t db) {
  if (ACC)
    asm volatile("wgmma.mma_async.sync.aligned.m64n128k16.f16.f16.f16 " D32 ", {%32,%33,%34,%35}, %36, 1, 1, 1, 1;\n"
                 : U32("+r", d, 0) : "r"(a[0]), "r"(a[1]), "r"(a[2]), "r"(a[3]), "l"(db));
  else
    asm volatile("wgmma.mma_async.sync.aligned.m64n128k16.f16.f16.f16 " D32 ", {%32,%33,%34,%35}, %36, 0, 1, 1, 1;\n"
                 : U32("=r", d, 0) : "r"(a[0]), "r"(a[1]), "r"(a[2]), "r"(a[3]), "l"(db));
}
template <int ACC, int TB> __device__ __forceinline__ void hmma_n32(uint32_t (&d)[8], const uint32_t (&a)[4], uint64_t db) {
  if (ACC)
    asm volatile("wgmma.mma_async.sync.aligned.m64n32k16.f16.f16.f16 " D8 ", {%8,%9,%10,%11}, %12, 1, 1, 1, %13;\n"
                 : U8("+r", d, 0) : "r"(a[0]), "r"(a[1]), "r"(a[2]), "r"(a[3]), "l"(db), "n"(TB));
  else
    asm volatile("wgmma.mma_async.sync.aligned.m64n32k16.f16.f16.f16 " D8 ", {%8,%9,%10,%11}, %12, 0, 1, 1, %13;\n"
                 : U8("=r", d, 0) : "r"(a[0]), "r"(a[1]), "r"(a[2]), "r"(a[3]), "l"(db), "n"(TB));
}
template <int ACC> __device__ __forceinline__ void hmma_n64t(uint32_t (&d)[16], const uint32_t (&a)[4], uint64_t db) {
  if (ACC)
    asm volatile("wgmma.mma_async.sync.aligned.m64n64k16.f16.f16.f16 " D16 ", {%16,%17,%18,%19}, %20, 1, 1, 1, 1;\n"
                 : U16("+r", d, 0) : "r"(a[0]), "r"(a[1]), "r"(a[2]), "r"(a[3]), "l"(db));
  else
    asm volatile("wgmma.mma_async.sync.aligned.m64n64k16.f16.f16.f16 " D16 ", {%16,%17,%18,%19}, %20, 0, 1, 1, 1;\n"
                 : U16("=r", d, 0) : "r"(a[0]), "r"(a[1]), "r"(a[2]), "r"(a[3]), "l"(db));
}
template <int N> __device__ __forceinline__ void fence_regs(uint32_t (&d)[N]) {
#pragma unroll
  for (int i = 0; i < N; i++) asm volatile("" : "+r"(d[i])::"memory");
}
__device__ __forceinline__ uint32_t hmul(uint32_t a, uint32_t b) { uint32_t r; asm("mul.rn.f16x2 %0, %1, %2;\n" : "=r"(r) : "r"(a), "r"(b)); return r; }
__device__ __forceinline__ uint32_t hfma(uint32_t a, uint32_t b, uint32_t c) { uint32_t r; asm("fma.rn.f16x2 %0, %1, %2, %3;\n" : "=r"(r) : "r"(a), "r"(b), "r"(c)); return r; }
__device__ __forceinline__ uint32_t hfnma(uint32_t a, uint32_t b, uint32_t c) {
  uint32_t r;
  asm("{\n.reg .b32 t;\nneg.f16x2 t, %1;\nfma.rn.f16x2 %0, t, %2, %3;\n}\n" : "=r"(r) : "r"(a), "r"(b), "r"(c));
  return r;
}
__device__ __forceinline__ uint32_t hrefl(uint32_t p, uint32_t s) {
  uint32_t r;
  asm("{\n.reg .b32 t;\nneg.f16x2 t, %2;\nfma.rn.f16x2 %0, %1, %3, t;\n}\n" : "=r"(r) : "r"(p), "r"(s), "r"(0x40004000u));
  return r;
}
__device__ __forceinline__ void bfly(uint32_t xr, uint32_t xi, uint32_t tr, uint32_t ti, uint32_t yr, uint32_t yi, uint32_t ur,
                                     uint32_t ui, uint32_t& sr, uint32_t& si, uint32_t& dr, uint32_t& di) {
  const uint32_t pr = hfnma(xi, ti, hmul(xr, tr)), pi = hfma(xi, tr, hmul(xr, ti));
  sr = hfnma(yi, ui, hfma(yr, ur, pr));
  si = hfma(yi, ur, hfma(yr, ui, pi));
  dr = hrefl(pr, sr);
  di = hrefl(pi, si);
}
template <int BH> __device__ __forceinline__ void fft_e1(const uint32_t (&d)[32], const uint32_t (&tw)[16], uint32_t (&a2)[2][2][4]) {
#pragma unroll
  for (int be = 0; be < 2; be++)
#pragma unroll
    for (int s = 0; s < 2; s++) {
      const int o = 16 * s + 8 * be + 2 * BH, p = 2 * BH;
      bfly(d[o], d[o + 1], tw[p], tw[p + 1], d[o + 4], d[o + 5], tw[p + 4], tw[p + 5], a2[be][0][s], a2[be][0][2 + s],
           a2[be][1][s], a2[be][1][2 + s]);
    }
}
__device__ __forceinline__ uint32_t hfms(uint32_t a, uint32_t b, uint32_t c) {
  uint32_t r;
  asm("{\n.reg .b32 t;\nneg.f16x2 t, %3;\nfma.rn.f16x2 %0, %1, %2, t;\n}\n" : "=r"(r) : "r"(a), "r"(b), "r"(c));
  return r;
}
template <int C, int J> __device__ __forceinline__ void fft_e2(const uint32_t (&d0)[8], const uint32_t (&d1)[8], uint32_t (&a3)[2][4]) {
  const uint32_t ur = d0[2 * J], ui = d0[4 + 2 * J], hr = d0[2 * J + 1], hi = d0[5 + 2 * J];
  const uint32_t vr = d1[2 * J], vi = d1[4 + 2 * J], gr = d1[2 * J + 1], gi = d1[5 + 2 * J];
  const uint32_t pr = hfnma(ui, hi, hmul(ur, hr)), pi = hfma(ui, hr, hmul(ur, hi));
  a3[0][2 + C] = pr;
  a3[0][C] = pi;
  a3[1][2 + C] = hfnma(vi, hi, hfma(vr, hr, hfnma(ui, gi, hfms(ur, gr, pi))));
  a3[1][C] = hfma(vi, hr, hfma(vr, hi, hfma(ui, gr, hfma(ur, gi, pr))));
}
__device__ __forceinline__ void fft_e3(const uint32_t (&d)[2][8], const uint32_t (&tw)[16], uint32_t zaddr) {
#pragma unroll
  for (int rho = 0; rho < 2; rho++) {
    uint32_t zr[4], zi[4];
#pragma unroll
    for (int nb = 0; nb < 4; nb++) {
      const uint32_t xi = d[nb >> 1][2 * (nb & 1) + rho], xr = d[nb >> 1][4 + 2 * (nb & 1) + rho];
      const uint32_t tr = tw[8 + 4 * rho + 2 * (nb & 1)], ti = tw[9 + 4 * rho + 2 * (nb & 1)];
      zr[nb] = hfnma(xi, ti, hmul(xr, tr));
      zi[nb] = hfma(xi, tr, hmul(xr, ti));
    }
    stsm4(zaddr + rho * 2048, zr[0], zr[1], zr[2], zr[3]);
    stsm4(zaddr + rho * 2048 + 1024, zi[0], zi[1], zi[2], zi[3]);
  }
}
__device__ __forceinline__ float bf_lo(uint32_t v) {
  uint32_t r;
  asm("prmt.b32 %0, %1, 0, 0x1044;\n" : "=r"(r) : "r"(v));
  return __uint_as_float(r);
}
__device__ __forceinline__ float bf_hi(uint32_t v) { return __uint_as_float(v & 0xffff0000u); }
__device__ __forceinline__ float ex2(float x) {
  float r;
  asm("ex2.approx.ftz.f32 %0, %1;\n" : "=f"(r) : "f"(x));
  return r;
}
__device__ __forceinline__ float rcp(float x) {
  float r;
  asm("rcp.approx.ftz.f32 %0, %1;\n" : "=f"(r) : "f"(x));
  return r;
}

__device__ __forceinline__ int g2_a(int s, int h) { return (((0xA1023 ^ (h * 0x11)) >> (4 * s)) & 15) * 16384; }
__device__ __forceinline__ int g2_b(int s) { return (((11 | 13 << 5 | 22 << 10 | 26 << 15 | 24 << 20) >> (5 * s)) & 31) * 8192; }
static_assert(OFF_U == 10 * 16384 && OFF_H == 12 * 16384 && OFF_OP == 2 * 16384 && OFF_Q + 6 * 4096 == 11 * 8192, "units");
__device__ __forceinline__ int g2_k(int hp, int i) {
  return i < 2 ? hp ^ 1 ^ i : i < 4 ? (hp & ~1) ^ i : ((hp & ~3) + i) & 15; }
__device__ __forceinline__ int y_slot(int wg, int it) {
  static_assert(T_B2 == T_TW + 8192 && T_A1 == T_B2 + 4096, "y slots");
  return OFF_T + T_TW + ((it + 3) & 3) * 4096 + wg * 2048;
}

__device__ __forceinline__ void to_arr(uint32_t (&d)[4], uint4 v) { d[0] = v.x; d[1] = v.y; d[2] = v.z; d[3] = v.w; }

__device__ __forceinline__ void attn_stage(uint32_t sb, int blk, int lane, const float (&acc)[96], uint32_t (&k1)[2][4]) {
  const int lr = lane & 7, lm = lane >> 3;
  const uint32_t base = sb + OFF_VP + (blk * 16 + lr + 8 * (lm & 1)) * 128;
#pragma unroll
  for (int i = 0; i < 8; i++) k1[i >> 2][i & 3] = pack_bf16(acc[34 + 4 * i], acc[35 + 4 * i]);
  const uint32_t kh = sb + OFF_OP + ((blk + 1) & 15) * 2048 + lane * 16;
  sts128(kh, k1[0][0], k1[0][1], k1[0][2], k1[0][3]);
  sts128(kh + 512, k1[1][0], k1[1][1], k1[1][2], k1[1][3]);
#pragma unroll
  for (int j = 0; j < 8; j += 2)
    stsm4(base + (((j + (lm >> 1)) ^ lr) << 4), pack_bf16(acc[64 + 4 * j], acc[65 + 4 * j]),
          pack_bf16(acc[66 + 4 * j], acc[67 + 4 * j]), pack_bf16(acc[68 + 4 * j], acc[69 + 4 * j]),
          pack_bf16(acc[70 + 4 * j], acc[71 + 4 * j]));
}
__device__ __forceinline__ void attn_pack(const float (&acc)[96], uint32_t (&qa)[2][8], uint32_t (&k0)[2][4]) {
#pragma unroll
  for (int hd = 0; hd < 2; hd++) {
#pragma unroll
    for (int i = 0; i < 8; i++) {
      asm volatile("cvt.rn.bf16x2.f32 %0, %1, %2;\n" : "=r"(qa[hd][i]) : "f"(acc[16 * hd + 2 * i + 1]), "f"(acc[16 * hd + 2 * i]));
    }
#pragma unroll
    for (int i = 0; i < 4; i++) {
      asm volatile("cvt.rn.bf16x2.f32 %0, %1, %2;\n" : "=r"(k0[hd][i]) : "f"(acc[33 + 16 * hd + 4 * i]), "f"(acc[32 + 16 * hd + 4 * i]));
    }
  }
}
__device__ __forceinline__ void attn_own(const uint32_t (&k0)[2][4], const uint32_t (&k1)[2][4], bool le0, bool le1,
                                         const uint32_t (&qa)[2][8], float (&l)[2][4]) {
#pragma unroll
  for (int hd = 0; hd < 2; hd++) {
    float s0[4], s1[4];
    mma16816_z(s0, qa[hd][0], qa[hd][1], qa[hd][2], qa[hd][3], k0[hd][0], k0[hd][1]);
    mma16816_z(s1, qa[hd][0], qa[hd][1], qa[hd][2], qa[hd][3], k1[hd][0], k1[hd][1]);
    mma16816(s0, qa[hd][4], qa[hd][5], qa[hd][6], qa[hd][7], k0[hd][2], k0[hd][3]);
    mma16816(s1, qa[hd][4], qa[hd][5], qa[hd][6], qa[hd][7], k1[hd][2], k1[hd][3]);
    l[hd][0] = s0[0];
    l[hd][1] = s0[1];
    l[hd][2] = le0 ? s1[2] : s0[2];
    l[hd][3] = le1 ? s1[3] : s0[3];
  }
}
template <int N> __device__ __forceinline__ void quad_softmax(float (&x)[N][2], uint32_t (&pp)[N]) {
  const float c2 = 1.4426950408889634f;
  uint32_t q[N], mx[N / 2];
#pragma unroll
  for (int n = 0; n < N; n++) {
    const uint32_t r = pack_bf16(x[n][0], x[n][1]);
    q[n] = bfma2(r, 0x3e353e35u, bmul2(r, 0x379e379eu));
    x[n][0] = bf_lo(q[n]);
    x[n][1] = bf_hi(q[n]);
  }
#pragma unroll
  for (int n = 0; n < N / 2; n++)
    mx[n] = bmax2(__byte_perm(q[2 * n], q[2 * n + 1], 0x5410), __byte_perm(q[2 * n], q[2 * n + 1], 0x7632));
#pragma unroll
  for (int o = 1; o <= 2; o++)
#pragma unroll
    for (int n = 0; n < N / 2; n++) mx[n] = bmax2(mx[n], __shfl_xor_sync(0xffffffffu, mx[n], o));
  float m[N], t[N];
#pragma unroll
  for (int n = 0; n < N / 2; n++) {
    m[2 * n] = bf_lo(mx[n]);
    m[2 * n + 1] = bf_hi(mx[n]);
  }
#pragma unroll
  for (int n = 0; n < N; n++) {
    const float nm = -m[n] * c2;
    x[n][0] = ex2(fmaf(x[n][0], c2, nm));
    x[n][1] = ex2(fmaf(x[n][1], c2, nm));
    t[n] = x[n][0] + x[n][1];
  }
#pragma unroll
  for (int o = 1; o <= 2; o++)
#pragma unroll
    for (int n = 0; n < N; n++) t[n] += __shfl_xor_sync(0xffffffffu, t[n], o);
#pragma unroll
  for (int n = 0; n < N; n++) {
    const float inv = rcp(t[n]);
    pp[n] = pack_bf16(x[n][0] * inv, x[n][1] * inv);
  }
}
__device__ __forceinline__ void attn_pv(uint32_t dst, const uint32_t (&va)[4], const uint32_t (&vb)[4], uint32_t pp,
                                        uint32_t maskLE) {
  const uint32_t b0 = pp & ~maskLE, b1 = pp & maskLE;
  float oa[4], ob[4];
  mma16816_z(oa, va[0], va[1], va[2], va[3], b0, b1);
  mma16816_z(ob, vb[0], vb[1], vb[2], vb[3], b0, b1);
  stsm4t(dst, pack_bf16(oa[0], oa[1]), pack_bf16(oa[2], oa[3]), pack_bf16(ob[0], ob[1]), pack_bf16(ob[2], ob[3]));
}

template <int MODE>
__global__ void __cluster_dims__(2, 1, 1) __launch_bounds__(NTHREADS, 1)
fused_kernel(const Params p, const __grid_constant__ CUtensorMap tmX, const __grid_constant__ CUtensorMap tmW,
             const __grid_constant__ CUtensorMap tmWo,
             const __grid_constant__ CUtensorMap tmQ,
             const __grid_constant__ CUtensorMap tmXh, const __grid_constant__ CUtensorMap tmWh) {
  extern __shared__ __align__(1024) uint8_t smem[];
  const uint32_t sb = smem_u32(smem) + HALO;
  const uint32_t bars = sb + OFF_BAR;
  const int tid = threadIdx.x, lane = tid & 31, warp = __shfl_sync(0xffffffffu, tid >> 5, 0);
  const int rank = blockIdx.x & 1;
  const bool halo_cta = blockIdx.x < 4;
  if (halo_cta && MODE != 0) return;
  int grp, mem;
  {
    const int t = (blockIdx.x >> 1) - 4, u = t - 32;
    const int q7 = (u * 37) >> 8;
    const bool lo = (unsigned)t < 32u, mid = (unsigned)u < 28u;
    grp = lo ? (t & 7) : (mid ? 1 + u - 7 * q7 : 0);
    mem = lo ? (t >> 3) : (mid ? 4 + q7 : (t < 0 ? t + 6 : t - 54));
  }
  const int rg = (grp >> 2) * 4 + (mem >> 1), hp = (grp & 3) * 4 + (mem & 1) * 2 + rank;
  const int rb2 = (grp >> 2) * 8 + mem, cb2 = (grp & 3) * 2 + rank;
  const int chb = grp * 16 + mem * 2 + rank;
  const int cta = rg * 16 + hp;
  const int par = rg >> 2, gidx = rg & 3;

  if (tid < 256 && !halo_cta && MODE != 2) {
    const int r = tid >> 3, c = tid & 7;
    const uint32_t so = r * 128 + ((c ^ (r & 7)) << 4);
    const __nv_bfloat16* wg0 = p.w + (size_t)r * (3 * DM) + hp * 64 + c * 8;
    const __nv_bfloat16* xg0 = p.x + (size_t)(2 * (gidx * 256 + r) + par) * DM + c * 8;
#pragma unroll
    for (int j = 0; j < 3; j++) cp_async16n(sb + OFF_1B + j * 4096 + so, wg0 + j * DM);
#pragma unroll
    for (int i = 0; i < 8; i++) cp_async16n(sb + i * 4096 + so, xg0 + (size_t)i * 64 * DM);
    asm volatile("cp.async.commit_group;\n" ::: "memory");
  }
  if (tid == 256) {
    prefetch_tmap(halo_cta ? &tmXh : &tmX);
#pragma unroll
    for (int i = 0; i < NS1B; i++) mbar_init(bars + 8 * (BAR_FULLB + i), 1);
#pragma unroll
    for (int i = 0; i < NS1A; i++) mbar_init(bars + 8 * (BAR_FULLA + i), 1);
    asm volatile("fence.mbarrier_init.release.cluster;\n" ::: "memory");
    if (!halo_cta && MODE != 2) {
      mbar_expect_tx(bars + 8 * (BAR_FULLB + 1), STG1B);
      tma_load_3d(sb + OFF_1B + 1 * STG1B, &tmW, bars + 8 * (BAR_FULLB + 1), hp * 64, 32, 0);
      mbar_expect_tx(bars + 8 * (BAR_FULLB + 2), STG1B);
      tma_load_3d(sb + OFF_1B + 2 * STG1B, &tmW, bars + 8 * (BAR_FULLB + 2), hp * 64, 64, 0);
    } else {
      prefetch_tmap(&tmWh);
    }
  } else if (tid == 288) {
#pragma unroll
    for (int i = 0; i < NS1A; i++) mbar_init(bars + 8 * (BAR_EMPTYA + i), 4);
#pragma unroll
    for (int i = 0; i < NS1B; i++) mbar_init(bars + 8 * (BAR_EMPTYB + i), 2);
    asm volatile("fence.mbarrier_init.release.cluster;\n" ::: "memory");
  } else if (tid == 320) {
#pragma unroll
    for (int i = 0; i < NS2; i++) {
      mbar_init(bars + 8 * (BAR_FULL2 + i), 1);
      mbar_init(bars + 8 * (BAR_EMPTY2 + i), 4);
    }
    mbar_init(bars + 8 * BAR_DEAD, 2);
    mbar_init(bars + 8 * (BAR_DEAD + 1), 2);
    mbar_init(bars + 8 * BAR_X, 2);
    mbar_init(bars + 8 * BAR_REL, 2);
    asm volatile("fence.mbarrier_init.release.cluster;\n" ::: "memory");
  } else if (tid == 352) {
    mbar_init(bars + 8 * BAR_T, 1);
    mbar_init(bars + 8 * BAR_UH, 3);
    mbar_init(bars + 8 * BAR_LFREE, 4);
    mbar_init(bars + 8 * BAR_LAND, 1);
    mbar_init(bars + 8 * BAR_U, 1);
    mbar_init(bars + 8 * BAR_Q, 1);
    mbar_init(bars + 8 * BAR_STG, 9);
    asm volatile("fence.mbarrier_init.release.cluster;\n" ::: "memory");
  }
  if (warp == 8) PROF2(23);
  cluster_sync_all();
  if (warp == 8) PROF2(24);

  if (warp >= 8) {
    const int hw = warp - 8;
    const int lr = lane & 7, lm = lane >> 3;
    auto g1_issue_a = [&](int j, int s) {
      const uint32_t fb = bars + 8 * (BAR_FULLA + s);
      mbar_expect_tx(fb, STG1A);
      tma_load_3d_mc(sb + s * STG1A + rank * 16384, &tmX, fb, j * 64, par, gidx * 256 + rank * 128);
    };
    auto g1_issue_b = [&](int kb, int s) {
      const uint32_t fb = bars + 8 * (BAR_FULLB + s);
      mbar_expect_tx(fb, STG1B);
      tma_load_3d(sb + OFF_1B + s * STG1B, &tmW, fb, hp * 64, kb * 32, 0);
    };
    asm volatile("setmaxnreg.dec.sync.aligned.u32 %0;\n" :: "n"(REG_HELP));

    if (halo_cta) {
      if (hw == 0) {
        int s = 0, ph = 1;
#pragma unroll 1
        for (int kb = 0; kb < 16; kb++) {
          mbar_wait(bars + 8 * (BAR_EMPTYB + s), ph);
          const uint32_t fb = bars + 8 * (BAR_FULLB + s), st = sb + s * STGH;
          if (elect_one()) {
            mbar_expect_tx(fb, STGH);
            tma_load_4d(st, &tmXh, fb, kb * 64, 248, 0, 0);
            tma_load_3d(st + 8192, &tmWh, fb, 0, kb * 64, 16 + blockIdx.x * 4);
            tma_load_3d(st + 8192 + 32768, &tmWh, fb, 0, kb * 64, 32 + blockIdx.x * 4);
          }
          if (++s == 3) { s = 0; ph ^= 1; }
        }
      }
      __syncwarp();
    } else if (hw == 0) {
      uint32_t epoch = 0;
      if (lane < (MODE == 2 ? NS2 : 2)) mbar_arrive_cluster_n(mapa(bars, rank) + 8 * (BAR_EMPTY2 + lane), 4);
      if (MODE != 2) {
      epoch = ld_relaxed(g_flag_o + 2 * cta) + 1;
      if (lane == 0) {
        mbar_expect_tx(bars + 8 * BAR_U, 32768);
        mbar_expect_tx(bars + 8 * BAR_LAND, 32768 + 64);
        mbar_expect_tx(bars + 8 * BAR_Q, 32768);
        mbar_expect_tx(bars + 8 * BAR_T, T_END);
      }
      {
        int sa = 1, pha = 1, sbb = 2, phb = 1;
#pragma unroll 1
        for (int kb = 2; kb < 32; kb++) {
          if (!(kb & 1)) {
            mbar_wait(bars + 8 * (BAR_EMPTYA + sa), pha);
            if (elect_one()) g1_issue_a(kb >> 1, sa);
            if (++sa == NS1A) { sa = 0; pha ^= 1; }
          }
          mbar_wait(bars + 8 * (BAR_EMPTYB + sbb), phb);
          if (kb > 2 && elect_one()) g1_issue_b(kb, sbb);
          __syncwarp();
          if (kb >= PF0 && kb < PF0 + 12)
            prefetch_l2((kb < PF0 + 8 ? p.q + (size_t)chb * 16384 + (kb - PF0) * 2048 : p.wo + (size_t)chb * 8192 + (kb - PF0 - 8) * 2048) + lane * 64);
          if (kb == 4) PROF2(27);
          if (kb == 1) PROF2(38);
          if (kb == 2) PROF2(39);
          if (++sbb == NS1B) { sbb = 0; phb ^= 1; }
        }
      }
      static_assert(32 % NS1B == 2 && (32 / NS1B) % 2 == 0 && OFF_Q + STG2 + 6 * 4096 == OFF_1B + 2 * STG1B, "slots / parity of these loads");
      const uint8_t* tab = reinterpret_cast<const uint8_t*>(g_tab);
      if (lane == 0) {
        prefetch_tmap(&tmWo);
        prefetch_tmap(&tmQ);
        bulk_load(sb + OFF_T + T_A1, tab + T_A1, T_END - T_A1, bars + 8 * BAR_T);
        mbar_wait(bars + 8 * (BAR_EMPTYB + 2), 1);
        tma_load_5d(sb + OFF_Q + STG2 + 6 * 4096, &tmQ, bars + 8 * BAR_Q, (chb & ~1) * 8, rank * 32 + 24);
        tma_load_5d(sb + OFF_Q + STG2 + 7 * 4096, &tmQ, bars + 8 * BAR_Q, (chb & ~1) * 8, rank * 32 + 28);
        if (gidx != 0) wait_flag(g_flag_h + (hp >> 2), epoch);
      }
      __syncwarp();
      {
        uint4 hk0 = make_uint4(0, 0, 0, 0), hk1 = hk0, hv0 = hk0, hv1 = hk0;
        if (gidx != 0) {
          const uint4* src = g_halo + cta * 128 + lane;
          hk0 = __ldcg(src); hk1 = __ldcg(src + 32); hv0 = __ldcg(src + 64); hv1 = __ldcg(src + 96);
        }
        if (lane == 0) {
          mbar_wait(bars + 8 * (BAR_EMPTYB + 3), 1);
          bulk_load(sb + OFF_T, tab, T_TW, bars + 8 * BAR_T);
        }
        __syncwarp();
        PROF2(18);
        sts128(sb - HALO + lane * 16, hk0.x, hk0.y, hk0.z, hk0.w);
        sts128(sb - HALO + 512 + lane * 16, hk1.x, hk1.y, hk1.z, hk1.w);
        stsm4(sb - HALO + 1024 + lr * 128 + ((lm ^ lr) << 4), hv0.x, hv0.y, hv0.z, hv0.w);
        stsm4(sb - HALO + 1024 + lr * 128 + (((4 + lm) ^ lr) << 4), hv1.x, hv1.y, hv1.z, hv1.w);
        __syncwarp();
        if (lane == 0) {
          mbar_arrive(bars + 8 * BAR_STG);
          mbar_wait(bars + 8 * (BAR_EMPTYB + 4), 1);
          bulk_load(sb + OFF_T + T_TW, tab + T_TW, T_A1 - T_TW, bars + 8 * BAR_T);
#pragma unroll 1
          for (int i = 0; i < 6; i++) tma_load_5d(sb + OFF_Q + i * 4096, &tmQ, bars + 8 * BAR_Q, (chb & ~1) * 8, rank * 32 + i * 4);
          if (MODE == 0) {
            mbar_wait(bars + 8 * BAR_EMPTYB, 0);
            tma_load_3d(sb + g2_b(0), &tmWo, bars + 8 * BAR_FULL2, 0, g2_k(hp, 0) * 64, cb2 * 2);
            tma_load_3d(sb + g2_b(1), &tmWo, bars + 8 * (BAR_FULL2 + 1), 0, g2_k(hp, 1) * 64, cb2 * 2);
          }
        }
        __syncwarp();
      }
      }
      if (MODE != 1) {
        auto korder = [&](int i) { return MODE == 2 ? i : g2_k(hp, i); };
        const __nv_bfloat16* osrc = g_o + (size_t)(rb2 >> 1) * 16 * 16384 + ((rb2 & 1) * 2 + rank) * 4096;
        const uint32_t* flag = g_flag_o + ((rb2 >> 1) * 32 + korder(lane & 15) * 2 + (rb2 & 1));
        uint32_t ready = MODE == 0 ? 0u : ~0u, pv = 0;
        const __nv_bfloat16* o23[2] = {osrc + korder(2) * 16384, osrc + korder(3) * 16384};
        if (MODE == 0) {
          asm volatile("" : "+l"(o23[0]), "+l"(o23[1]), "+l"(flag));
          if (lane < 4 && lane != 1) mbar_expect_tx(bars + 8 * (BAR_FULL2 + lane), STG2);
          mbar_wait_idle(bars + 8 * (BAR_EMPTY2 + 2), 0);
          mbar_wait(bars + 8 * (BAR_EMPTY2 + 3), 0);
          mbar_wait_idle(bars + 8 * BAR_REL, 0);
        }
#pragma unroll
        for (int i = MODE == 0 ? 2 : 0; i < 16; i++) {
          const int kb = korder(i), s = i % NS2, ph = (i / NS2) & 1;
          const uint32_t fb = bars + 8 * (BAR_FULL2 + s);
          if (!((ready >> i) & 1)) {
            int n = 0;
            do {
              ready |= __ballot_sync(0xffffffffu, ld_acquire(flag) == epoch);
            } while (!((ready >> i) & 1) && ++n < SPIN_LIMIT);
            fence_async_all();
          }
          if (i == 2) PROF(21);
          const bool pre = MODE == 0 && i < 4;
          if (!pre) mbar_wait(bars + 8 * (BAR_EMPTY2 + s), ph);
          if (elect_one()) {
            if (!pre) mbar_expect_tx(fb, STG2);
            asm volatile(
                "cp.async.bulk.shared::cluster.global.mbarrier::complete_tx::bytes.multicast::cluster [%0], [%1], %2, [%3], %4;\n"
                ::"r"(sb + g2_a(s, rb2 & 1) + rank * 8192), "l"(pre ? o23[i & 1] : osrc + kb * 16384), "r"(8192), "r"(fb), "h"((uint16_t)3) : "memory");
            if (!pre) tma_load_3d(sb + g2_b(s), &tmWo, fb, 0, kb * 64, cb2 * 2);
          }
          if (MODE == 0 && i == 3) pv = ld_relaxed(flag);
          if (MODE == 0 && i == 4) {
            ready |= __ballot_sync(0xffffffffu, pv == epoch);
            asm volatile("fence.acquire.gpu;\n" ::: "memory");
            fence_async_all();
          }
          if (i == 3) PROF(37);

        }
      }
      __syncwarp();
    } else if (MODE != 2) {
      {
        const int g = lane >> 2, t = lane & 3;
        uint32_t w[2][4];
#pragma unroll
        for (int h = 0; h < 2; h++) {
          const uint2 x = __ldg(reinterpret_cast<const uint2*>(p.shift_k + ((chb & ~1) * 8 + h * 8 + g) * 4));
          w[h][0] = __byte_perm(x.x, x.x, 0x1010);
          w[h][1] = __byte_perm(x.x, x.x, 0x3232);
          w[h][2] = __byte_perm(x.y, x.y, 0x1010);
          w[h][3] = __byte_perm(x.y, x.y, 0x3232);
        }
        auto swz = [](int r) { return (((r & 29) | ((r ^ (r >> 2)) & 2)) << 5) | (r & 16); };
        const uint32_t kring = sb + OFF_H + (hw - 1) * 8192, vring = kring + 4096;
        const int s0 = rank * 32 + (hw - 1) * 11, s1 = hw == 3 ? rank * 32 + 32 : s0 + 11;
        const size_t goff = (size_t)(lane >> 1) * DM + (chb & ~1) * 8 + (lane & 1) * 8;
        const __nv_bfloat16* kg = p.k + goff;
        const __nv_bfloat16* vg = p.v + goff;
        const uint32_t d0 = swz(lane >> 1) ^ ((lane & 1) << 4), d1 = swz(16 + (lane >> 1)) ^ ((lane & 1) << 4);
        auto issue = [&](int st) {
          const uint32_t so = (st & 3) << 10;
          cp_async16(kring + so + d0, kg + (size_t)st * 32 * DM, 16);
          cp_async16(kring + so + d1, kg + (size_t)(st * 32 + 16) * DM, 16);
          cp_async16(vring + so + d0, vg + (size_t)st * 32 * DM, 16);
          cp_async16(vring + so + d1, vg + (size_t)(st * 32 + 16) * DM, 16);
        };
        const int xa = 8 * (lr >> 1) + 2 * lm + (lr & 1), xb = 8 * (lr >> 1) - 4 + 2 * (lm & 1) + (lr & 1);
        const uint32_t la = swz(xa), lb = swz(xb & 31);
        const int backb = xb < 0 ? 1 : 0;
        const uint32_t ud[2] = {mapa(sb + OFF_U + g * 4096 + t * 16, 0), mapa(sb + OFF_U + g * 4096 + t * 16, 1)};
        const uint32_t ub[2] = {mapa(bars + 8 * BAR_U, 0), mapa(bars + 8 * BAR_U, 1)};
        if (lane == 0) mbar_wait(bars + 8 * (BAR_FULLB + NS1B - 1), 0);
        __syncwarp();
        if (lane >= 24) cp_async16(kring + (((s0 - 1) & 3) << 10) + d1, s0 > 0 ? kg + (size_t)(s0 * 32 - 16) * DM : kg, s0 > 0 ? 16 : 0);
        issue(s0);
        asm volatile("cp.async.commit_group;\n" ::: "memory");
        issue(s0 + 1);
        asm volatile("cp.async.commit_group;\n" ::: "memory");
#pragma unroll 1
        for (int st = s0; st < s1; st++) {
          if (st + 2 < s1) issue(st + 2);
          if (hw == 1 && st - s0 < 8) prefetch_l2(p.ssm_k + (size_t)(chb * 8 + st - s0) * SEQ + lane * 64);
          if (hw == 2 && st == s0 + 4 && lane < 2) prefetch_l2(g_tab + (chb * 2 + lane) * 32);
          const uint32_t uo = (st ^ ((g ^ (st >> 2)) & 1)) * 64;
          asm volatile("cp.async.commit_group;\n" ::: "memory");
          asm volatile("cp.async.wait_group 2;\n" ::: "memory");
          __syncwarp();
#pragma unroll
          for (int h = 0; h < 2; h++) {
            uint32_t e[6], vv[4], e4[4];
            ldsm4t(e4, kring + ((st & 3) << 10) + (la ^ (h << 4)));
            ldsm2t(e[0], e[1], kring + (((st - backb) & 3) << 10) + (lb ^ (h << 4)));
            ldsm4t(vv, vring + ((st & 3) << 10) + (la ^ (h << 4)));
            e[2] = e4[0]; e[3] = e4[1]; e[4] = e4[2]; e[5] = e4[3];
            uint32_t o[5];
#pragma unroll
            for (int i = 0; i < 5; i++) o[i] = __byte_perm(e[i], e[i + 1], 0x5432);
#pragma unroll
            for (int i = 0; i < 4; i++) {
              uint32_t a = bmul2(o[i], w[h][3]);
              a = bfma2(e[i + 1], w[h][2], a);
              a = bfma2(o[i + 1], w[h][1], a);
              a = bfma2(e[i + 2], w[h][0], a);
              vv[i] = bmul2(a, vv[i]);
            }
            st_async128(ud[h] + uo, ub[h], vv[0], vv[1], vv[2], vv[3]);
          }
          __syncwarp();
        }
        PROF(16);
      }
      {
        const int rw = (lane >> 3) + (lane & 4), ck = lane & 3;
        const uint32_t so = rw * 64 + ck * 16, dof = rw * 128 + ((ck ^ rw) << 4);
        const uint8_t* hsrc = reinterpret_cast<const uint8_t*>(p.ssm_k + (size_t)chb * 8 * SEQ) + so;
        const float dv = lane < 8 ? __bfloat162float(p.ssm_D[chb * 8 + lane]) : 0.f;
        uint32_t x[32];
        auto load = [&](const uint8_t* src, int i) {
          asm volatile("ld.v4.u32 {%0,%1,%2,%3}, [%4];\n" : "=r"(x[4 * i]), "=r"(x[4 * i + 1]), "=r"(x[4 * i + 2]), "=r"(x[4 * i + 3])
                       : "l"(src + i * 512) : "memory");
        };
#pragma unroll
        for (int i = 0; i < 8; i++) load(hsrc + (hw - 1) * 4096, i);
        nb_sync(NB_HELP3, 96);
        mbar_wait(bars + 8 * BAR_U, 0);
        int eh = 0;
#pragma unroll 1
        for (int n = 2 * (hw - 1); n < 16; n += (n & 1) ? 5 : 1) {
          const int c = n >> 1;
          const uint8_t* nsrc = (n & 1) ? hsrc + (c < 5 ? c + 3 : c) * 4096
                                        : smem + HALO + OFF_U + c * 4096 + (so ^ (((c ^ (lane >> 2)) & 1) << 6));
          const uint32_t dst = sb + ((n & 1) ? OFF_U : OFF_H) + c * 4096 + dof;
          const float dc = __shfl_sync(0xffffffffu, dv, c);
          const float h0 = bf_lo(x[0]) + ((lane | (n & 1)) == 0 ? dc : 0.f), h1 = bf_hi(x[0]);
          x[0] = pack_bf16(h0, h1);
          uint32_t m[2] = {x[0], x[1]};
#pragma unroll
          for (int i = 2; i < 32; i++) asm("max.xorsign.abs.bf16x2 %0, %0, %1;\n" : "+r"(m[i & 1]) : "r"(x[i]));
          asm("max.xorsign.abs.bf16x2 %0, %0, %1;\n" : "+r"(m[0]) : "r"(m[1]));
          const uint32_t e = max(__reduce_max_sync(0xffffffffu, max((m[0] >> 7) & 255u, (m[0] >> 23) & 255u)), 5u);
          const uint32_t sc = (259u - e) * 0x00800080u;
#pragma unroll
          for (int i = 0; i < 8; i++) {
            uint32_t o[4];
#pragma unroll
            for (int j = 0; j < 4; j++) {
              const uint32_t v = bmul2(x[4 * i + j], sc);
              asm("cvt.rn.f16x2.f32 %0, %1, %2;\n" : "=r"(o[j]) : "f"(bf_hi(v)), "f"(i + j == 0 ? h0 * bf_hi(sc) : bf_lo(v)));
            }
            sts128((dst + (i & 3) * 1024) ^ ((i >> 2) << 6), o[0], o[1], o[2], o[3]);
            load(nsrc, i);
          }
          if (n & 1) {
            const int f = min(max((int)e + eh - 129, 0), 254);
            if (lane < 2)
              asm volatile("st.async.weak.shared::cluster.mbarrier::complete_tx::bytes.b32 [%0], %2, [%1];\n"
                           ::"r"(mapa(sb + OFF_SC + rank * 32 + c * 4, lane)), "r"(mapa(bars + 8 * BAR_LAND, lane)), "r"(f << 7) : "memory");
          }
          eh = e;
        }
        fence_async_smem();
        __syncwarp();
        if (lane == 0) mbar_arrive(bars + 8 * BAR_UH);
        PROF(32);
      }
      if (hw < 3) {
        const uint32_t rb = mapa(bars, lane & 1);
        const uint32_t epoch = ld_relaxed(g_flag_o + (2 * cta + hw - 1)) + 1;
        const bool own = hw - 1 == (rb2 & 1);
        nb_sync(NB_OREADY + hw - 1, 160);
        if (lane == 0) {
          asm volatile("cp.async.bulk.global.shared::cta.bulk_group [%0], [%1], %2;\n" ::"l"(g_o + (size_t)cta * 16384 + (hw - 1) * 8192),
                       "r"(sb + OFF_OP + (hw - 1) * 16384), "r"(16384) : "memory");
          bulk_commit();
        }
        if (lane < 2) {
          mbar_arrive_cluster(rb + 8 * (BAR_EMPTY2 + 2));
          mbar_arrive_cluster(rb + 8 * (BAR_EMPTY2 + 3));
        }
        if (lane == 0) {
          bulk_wait0();
          if (own) mbar_expect_tx(bars + 8 * (BAR_FULL2 + 1), 16384);
          mbar_arrive_cluster(mapa(bars, own ? rank : rank ^ 1) + 8 * BAR_X);
          st_release(g_flag_o + (2 * cta + hw - 1), epoch);
          mbar_arrive(bars + 8 * BAR_REL);
        }
        __syncwarp();
        PROF(own ? 17 : 19);
      } else {
        if (MODE == 0) {
          mbar_wait_idle(bars + 8 * BAR_X, 0);
          if (elect_one())
            asm volatile("cp.async.bulk.shared::cluster.shared::cta.mbarrier::complete_tx::bytes [%0], [%1], %2, [%3];\n"
                         ::"r"(mapa(sb + g2_a(0, rb2 & 1), rank ^ 1)), "r"(sb + g2_a(1, rb2 & 1)), "r"(16384),
                         "r"(mapa(bars + 8 * BAR_FULL2, rank ^ 1)) : "memory");
        }
        if (MODE == 0) {
          mbar_wait_idle(bars + 8 * BAR_DEAD, 0);
          if (elect_one()) {
            tma_load_3d(sb + g2_b(2), &tmWo, bars + 8 * (BAR_FULL2 + 2), 0, g2_k(hp, 2) * 64, cb2 * 2);
            tma_load_3d(sb + g2_b(3), &tmWo, bars + 8 * (BAR_FULL2 + 3), 0, g2_k(hp, 3) * 64, cb2 * 2);
          }
        }
        __syncwarp();
      }
    }
    if (!halo_cta && MODE != 2) {
      {
        const int c8 = (4 * (lr >> 1) + 2 * (lm & 1) + (lr & 1)) & 7;
        const bool own = (lr >> 2) == rank;
        const uint32_t ya = sb + (own ? y_slot(c8 & 1, c8 >> 1) : OFF_LAND + c8 * 2048);
        const uint32_t yx = ((lm >> 1) ^ lr) << 4;
        const int row = (lane >> 4) * 8 + ((lane >> 3) & 1) * 16 + ((lane >> 2) & 1);
        uint2* og = reinterpret_cast<uint2*>(p.out + (size_t)(rank * 1024 + row) * (2 * DM) + (chb & ~1) * 8 + (lane & 3) * 4);
        const uint32_t qa = sb + OFF_Q + (lane >> 4) * 512 + (lane & 15) * 8;
        mbar_wait(bars + 8 * BAR_Q, 0);
        mbar_wait_idle(bars + 8 * BAR_LAND, 0);
        PROF(33);
        const uint32_t t0 = clock();
        const uint4 s4 = lds128(sb + OFF_SC + (lane & 3) * 16);
        const uint32_t sc[2] = {s4.x | (s4.y << 16), s4.z | (s4.w << 16)};
        auto fin = [&](uint32_t q2, uint32_t y2, uint32_t s2) {
          float lo, hi;
          asm("{\n.reg .b16 l, h;\nmov.b32 {l, h}, %2;\ncvt.f32.f16 %0, l;\ncvt.f32.f16 %1, h;\n}\n" : "=f"(lo), "=f"(hi) : "r"(y2));
          return bmul2(q2, bmul2(pack_bf16(lo, hi), s2));
        };
#pragma unroll 1
        for (int j = hw ? hw - 1 : 15; j < (hw ? 15 : 16); j += 3) {
          uint32_t y[4][4];
          uint2 q[8];
          while (hw && (uint32_t)clock() - t0 < j * PACE) __nanosleep(40);
          const uint32_t qj = qa + j * 2048 + (j >= 12 ? STG2 : 0);
#pragma unroll
          for (int i = 0; i < 4; i++) ldsm4t(y[i], ya + j * 128 + (yx ^ (i << 5)));
#pragma unroll
          for (int i = 0; i < 8; i++) q[i] = lds64(qj + (i >> 2) * 1024 + (i & 3) * 128);
#pragma unroll
          for (int i = 0; i < 8; i++) {
            og[(size_t)(j * 64 + (i >> 2) * 32 + (i & 3) * 2) * (2 * DM / 4)] =
                make_uint2(fin(q[i].x, y[i >> 1][2 * (i & 1)], sc[0]), fin(q[i].y, y[i >> 1][2 * (i & 1) + 1], sc[1]));
            if (i < 7) asm volatile("nanosleep.u32 40;\n" ::: "memory");
          }
        }
      }
      PROF(22);
    }
    cluster_sync_all();
  } else {
    asm volatile("setmaxnreg.inc.sync.aligned.u32 %0;\n" :: "n"(REG_MATH));
    if (warp == 0) PROF2(26);
    const int wg = warp >> 2;
    const int wtid = tid & 127;
    const bool signaller = (wtid == 0) || (wtid == 32);
    const uint32_t rbars = mapa(bars, wtid >> 5 & 1);

    if (halo_cta) {
      const uint32_t epoch = ld_relaxed(g_flag_h + blockIdx.x) + 1;
      float acc0[64], acc1[64];
      int s = 0, ph = 0;
#pragma unroll 1
      for (int kb = 0; kb < 16; kb++) {
        mbar_wait(bars + 8 * (BAR_FULLB + s), ph);
        const uint32_t st = sb + s * STGH;
        const uint64_t da = mkdesc(st, 16, 1024, 1);
        const uint64_t db = mkdesc(st + 8192 + wg * 32768, 8192, 1024, 1);
        wg_fence();
#pragma unroll
        for (int kk = 0; kk < 4; kk++) {
          wgmma_n128(acc0, da + 2 * kk, db + 128 * kk, kb + kk);
          wgmma_n128(acc1, da + 2 * kk, db + 1024 + 128 * kk, kb + kk);
        }
        wg_commit();
        wg_wait<0>();
        if (wtid == 0) mbar_arrive(bars + 8 * (BAR_EMPTYB + s));
        if (++s == 3) { s = 0; ph ^= 1; }
      }
      fence_regs(acc0);
      fence_regs(acc1);
      if ((warp & 3) != 3) {
#pragma unroll
        for (int hh = 0; hh < 2; hh++) {
          uint4* dst = g_halo + ((hh * 4 + (warp & 3) + 1) * 16 + blockIdx.x * 4) * 128 + wg * 64 + lane;
#pragma unroll
          for (int j = 0; j < 4; j++) {
            const int o = 16 * j + 2 * hh;
            dst[(j >> 1) * 128 + (j & 1) * 32] =
                make_uint4(pack_bf16(acc0[o], acc0[o + 1]), pack_bf16(acc0[o + 4], acc0[o + 5]),
                           pack_bf16(acc0[o + 8], acc0[o + 9]), pack_bf16(acc0[o + 12], acc0[o + 13]));
            dst[(2 + (j >> 1)) * 128 + (j & 1) * 32] =
                make_uint4(pack_bf16(acc1[o], acc1[o + 1]), pack_bf16(acc1[o + 4], acc1[o + 5]),
                           pack_bf16(acc1[o + 8], acc1[o + 9]), pack_bf16(acc1[o + 12], acc1[o + 13]));
          }
        }
      }
      nb_sync(NB_G1DONE, 256);
      if (tid == 0) st_release(g_flag_h + blockIdx.x, epoch);
      PROF(36);
      cluster_sync_all();
      return;
    }

    float acc[64];
    auto g2_step = [&](int s, int kb) {
      const uint64_t da = mkdesc(sb + g2_a(s, rb2 & 1) + wg * 8192, 16, 1024, 1);
      const uint64_t db = mkdesc(sb + g2_b(s), 8192, 1024, 1);
      wg_fence();
      wgmma_n128(acc, da, db, kb);
      wgmma_n128(acc, da + 2, db + 128, 1);
      wgmma_n128(acc, da + 4, db + 256, 1);
      wgmma_n128(acc, da + 6, db + 384, 1);
      wg_commit();
    };

    if (MODE != 2) {
    uint32_t a1[2][4], tw[16], d1[32];
    const uint32_t tb = sb + OFF_T + wtid * 16;
    const uint64_t dx = mkdesc(sb + OFF_U + wg * 4096, OFF_H - OFF_U, 1024, 1);
    auto s1 = [&](int it) {
      hmma_n128t<0>(d1, a1[0], dx + it * 512);
      hmma_n128t<1>(d1, a1[1], dx + it * 512 + 128);
      wg_commit();
    };
    auto ldtw = [&](int i) {
      const uint4 v = lds128(tb + T_TW + i * 2048);
      tw[4 * i] = v.x; tw[4 * i + 1] = v.y; tw[4 * i + 2] = v.z; tw[4 * i + 3] = v.w;
    };
    {
      float acc0[96], acc1[96];
      int sa = 0, pha = 0, sbb = 0, phb = 0;
      asm volatile("cp.async.wait_group 0;\n" ::: "memory");
      fence_async_smem();
      nb_sync(NB_FIRST, 256);
      if (tid == 0) {
        mbar_arrive(bars + 8 * BAR_FULLA);
        mbar_arrive(bars + 8 * BAR_FULLB);
      }
      PROF(0 + wg);
#pragma unroll 1
      for (int kb = 0; kb < 30; kb++) {
        if (!(kb & 1)) mbar_wait(bars + 8 * (BAR_FULLA + sa), pha);
        mbar_wait(bars + 8 * (BAR_FULLB + sbb), phb);
        if (kb == 0) PROF2(0 + wg);
        if (kb == 4 && wg == 0) PROF2(28);
        if (kb == 8 && wg == 0) PROF2(29);
        if (kb == 16 && wg == 0) PROF2(30);
        const uint64_t da = mkdesc(sb + sa * STG1A + wg * 16384 + (kb & 1) * 64, 16, 1024, 1);
        const uint64_t db = mkdesc(sb + OFF_1B + sbb * STG1B, 4096, 1024, 1);
        wg_fence();
        wgmma_n192(acc0, da, db, kb);
        wgmma_n192(acc1, da + 512, db, kb);
        wgmma_n192(acc0, da + 2, db + 128, 1);
        wgmma_n192(acc1, da + 514, db + 128, 1);
        wg_commit();
        wg_wait<1>();
        if (kb > 0) {
          if (wtid == 64) mbar_arrive(bars + 8 * (BAR_EMPTYB + (sbb == 0 ? NS1B - 1 : sbb - 1)));
          if (!(kb & 1) && signaller) mbar_arrive_cluster(rbars + 8 * (BAR_EMPTYA + (sa == 0 ? NS1A - 1 : sa - 1)));
        }
        if (++sbb == NS1B) { sbb = 0; phb ^= 1; }
        if ((kb & 1) && ++sa == NS1A) { sa = 0; pha ^= 1; }
      }
      const int blk0 = wg * 8 + (warp & 3);
      const int lr = lane & 7, lm = lane >> 3;
      const bool le0 = 2 * (lane & 3) <= (lane >> 2), le1 = 2 * (lane & 3) + 1 <= (lane >> 2);
      const uint32_t maskLE = (le0 ? 0x0000FFFFu : 0u) | (le1 ? 0xFFFF0000u : 0u);
      uint32_t k0[2][2][4], k1[2][2][4], qa[2][2][8];
      float l[2][2][4];
      {
        static_assert(15 % NS1A == 0 && 30 % NS1B == 0, "slots of the last k blocks");
        mbar_wait(bars + 8 * BAR_FULLA, 1);
        mbar_wait(bars + 8 * BAR_FULLB, 0);
        mbar_wait(bars + 8 * (BAR_FULLB + 1), 0);
        mbar_wait(bars + 8 * (BAR_EMPTYB + 2), 1);
        const uint64_t da = mkdesc(sb + wg * 16384, 16, 1024, 1);
        const uint64_t db = mkdesc(sb + OFF_1B, 4096, 1024, 1);
        wg_fence();
#pragma unroll
        for (int i = 0; i < 4; i++) wgmma_n192(acc0, da + 2 * i, db + (i >> 1) * (STG1B >> 4) + (i & 1) * 128, 1);
        wg_commit();
        wg_wait<1>();
        if (wtid == 64) mbar_arrive(bars + 8 * (BAR_EMPTYB + NS1B - 1));
#pragma unroll
        for (int i = 0; i < 2; i++) wgmma_n192(acc1, da + 512 + 2 * i, db + (i >> 1) * (STG1B >> 4) + (i & 1) * 128, 1);
        wg_commit();
        wg_wait<1>();
        fence_regs(acc0);
        attn_stage(sb, blk0, lane, acc0, k1[0]);
#pragma unroll
        for (int i = 2; i < 4; i++) wgmma_n192(acc1, da + 512 + 2 * i, db + (i >> 1) * (STG1B >> 4) + (i & 1) * 128, 1);
        wg_commit();
        attn_pack(acc0, qa[0], k0[0]);
        wg_wait<0>();
        fence_regs(acc1);
      }
      if (wtid == 64) mbar_arrive(bars + 8 * BAR_EMPTYB);
      PROF(2 + wg);
      attn_stage(sb, blk0 + 4, lane, acc1, k1[1]);
      __syncwarp();
      if (lane == 0) mbar_arrive(bars + 8 * BAR_STG);
      mbar_wait(bars + 8 * BAR_U, 0);
      attn_pack(acc1, qa[1], k0[1]);
      attn_own(k0[0], k1[0], le0, le1, qa[0], l[0]);
      attn_own(k0[1], k1[1], le0, le1, qa[1], l[1]);
      static_assert(OFF_VP == 0, "halo V rows");
      const uint32_t vl0 = sb + OFF_VP - 1024 + blk0 * 2048 + (lm >> 1) * 1024 + lr * 128 + (((lm & 1) ^ lr) << 4);
      const uint32_t vl[4] = {vl0, vl0 ^ 64, vl0 ^ 32, vl0 ^ 96};
      const uint32_t obase = sb + OFF_OP + (blk0 * 16 + lr) * 128 + ((lm ^ lr) << 4);
      mbar_wait(bars + 8 * BAR_STG, 0);
      {
        uint32_t km[4][4], va[8][4], vb[8][4], pp[8];
        float x[8][2];
#pragma unroll
        for (int n = 0; n < 4; n++) {
          const int blk = blk0 + 4 * (n >> 1);
          to_arr(km[n], lds128(sb + (blk == 0 ? -HALO : OFF_OP + blk * 2048) + (n & 1) * 512 + lane * 16));
        }
#pragma unroll
        for (int n = 0; n < 8; n++) {
          const uint32_t o = ((n >> 1) & 1) * 8192 + (n >> 2) * 1024;
          ldsm4t(va[n], vl[n & 1] + o);
          ldsm4t(vb[n], vl[2 + (n & 1)] + o);
        }
        const bool first = blk0 == 0 && gidx == 0;
#pragma unroll
        for (int n = 0; n < 4; n++) {
          const uint32_t(&q)[8] = qa[n >> 1][n & 1];
          float sm[4];
          mma16816_z(sm, q[0], q[1], q[2], q[3], km[n][0], km[n][1]);
          mma16816(sm, q[4], q[5], q[6], q[7], km[n][2], km[n][3]);
          if (n < 2 && first) sm[0] = sm[1] = -1e9f / 0.17677669529663687f;
          x[n][0] = le0 ? l[n >> 1][n & 1][0] : sm[0];
          x[n][1] = le1 ? l[n >> 1][n & 1][1] : sm[1];
          x[4 + n][0] = l[n >> 1][n & 1][2];
          x[4 + n][1] = l[n >> 1][n & 1][3];
        }
        quad_softmax<8>(x, pp);
#pragma unroll
        for (int n = 7; n >= 0; n--)
          attn_pv((obase ^ ((n & 1) << 6)) + ((n >> 1) & 1) * 8192 + (n >> 2) * 1024, va[n], vb[n], pp[n], maskLE);
      }
      fence_async_smem();
      nb_arrive(NB_OREADY + wg, 160);
    }

    {
      const int w = warp & 3;
      uint32_t a4[8][4];
      uint32_t d4[16];
      PROF(34 + wg);
      const uint64_t dz = mkdesc(sb + OFF_U + wg * 4096, 1024, 128, 0);
      const uint64_t db2 = mkdesc(sb + OFF_T + T_B2, 128, 256, 0);
      mbar_wait(bars + 8 * BAR_T, 0);
      mbar_wait(bars + 8 * BAR_UH, 0);
      to_arr(a1[0], lds128(tb + T_A1));
      to_arr(a1[1], lds128(tb + T_A1 + 2048));
      wg_fence();
      s1(0);
      ldtw(0);
      ldtw(1);
      const uint32_t za = sb + (w < 2 ? OFF_U : OFF_H) + wg * 4096 + (w & 1) * 8192 + lane * 16;
      const uint32_t yl = (wtid ^ (4 * rank + wg)) * 16;
      const uint32_t yown = mapa(sb, rank) + yl, yrem = mapa(sb + OFF_LAND + wg * 2048, rank ^ 1) + yl;
      const uint32_t yb[2] = {mapa(bars + 8 * BAR_LAND, 0), mapa(bars + 8 * BAR_LAND, 1)};
      wg_wait<0>();
      fence_regs(d1);
      auto s4 = [&]() {
        wg_fence();
#pragma unroll
        for (int ks = 0; ks < 8; ks++) {
          const uint64_t d = dz + (ks & 1) * 128 + ((ks >> 1) & 1) * 512 + (ks >> 2) * ((OFF_H - OFF_U) >> 4);
          if (ks == 0) hmma_n64t<0>(d4, a4[ks], d);
          else hmma_n64t<1>(d4, a4[ks], d);
        }
        wg_commit();
      };
      auto e4 = [&](int pr) {
        fence_regs(d4);
        mbar_wait(bars + 8 * (pr == 0 ? BAR_LFREE : BAR_DEAD + 1), 0);
#pragma unroll
        for (int u = 0; u < 2; u++) {
          const int it = 2 * pr + u;
          const uint32_t o = (yown + y_slot(wg, it)) ^ (pr << 5), m = (yrem + it * 4096) ^ (pr << 5);
          st_async128(rank ? m : o, yb[0], d4[8 * u], d4[8 * u + 1], d4[8 * u + 2], d4[8 * u + 3]);
          st_async128(rank ? o : m, yb[1], d4[8 * u + 4], d4[8 * u + 5], d4[8 * u + 6], d4[8 * u + 7]);
        }
      };
      uint32_t a2[2][2][2][4], a3[2][2][4], d2[2][2][8], d3[2][8];
      auto s2a = [&]() {
        wg_fence();
#pragma unroll
        for (int c = 0; c < 4; c++) hmma_n32<0, 0>(d2[c & 1][c >> 1], a2[0][c & 1][c >> 1], db2 + (c >> 1) * 128);
      };
      auto s2b = [&]() {
        wg_fence();
#pragma unroll
        for (int c = 0; c < 4; c++) {
          hmma_n32<1, 0>(d2[c & 1][c >> 1], a2[1][c & 1][c >> 1], db2 + (c >> 1) * 128 + 64);
          if (c & 1) wg_commit();
        }
      };
      fft_e1<0>(d1, tw, a2[0]);
      s2a();
      fft_e1<1>(d1, tw, a2[1]);
      s2b();
      s1(1);
      ldtw(2);
      ldtw(3);
#pragma unroll
      for (int i = 0; i < 8; i++) to_arr(a4[i], lds128(tb + T_A4 + i * 2048));
#pragma unroll
      for (int it = 0; it < 4; it++) {
        if (it == 2) wg_wait<3>(); else if (it == 3) wg_wait<1>(); else wg_wait<2>();
        fence_regs(d2[0][0]);
        fence_regs(d2[1][0]);
        fft_e2<0, 0>(d2[0][0], d2[1][0], a3[0]);
        fft_e2<0, 1>(d2[0][0], d2[1][0], a3[1]);
        if (it == 2) wg_wait<2>(); else if (it == 3) wg_wait<0>(); else wg_wait<1>();
        fence_regs(d2[0][1]);
        fence_regs(d2[1][1]);
        fft_e2<1, 0>(d2[0][1], d2[1][1], a3[0]);
        fft_e2<1, 1>(d2[0][1], d2[1][1], a3[1]);
        wg_fence();
        hmma_n32<0, 0>(d3[0], a3[0][0], db2);
        hmma_n32<0, 0>(d3[1], a3[0][1], db2);
        hmma_n32<1, 0>(d3[0], a3[1][0], db2 + 64);
        hmma_n32<1, 0>(d3[1], a3[1][1], db2 + 64);
        wg_commit();
        if (it < 3) {
          wg_wait<1>();
          if (it == 2) {
            if (wtid == 64) mbar_arrive(bars + 8 * BAR_DEAD);
            e4(0);
          }
          fence_regs(d1);
          fft_e1<0>(d1, tw, a2[0]);
          s2a();
          wg_commit();
          wg_wait<1>();
        }
        if (it == 3) wg_wait<0>();
        if (it == 3 && wtid == 64) mbar_arrive(bars + 8 * (BAR_DEAD + 1));
        fence_regs(d3[0]);
        fence_regs(d3[1]);
        fft_e3(d3, tw, za + (it & 1) * 512);
        if (it < 3) {
          fft_e1<1>(d1, tw, a2[1]);
          s2b();
        }
        if (it & 1) {
          fence_async_smem();
          nb_sync(NB_WG + wg, 128);
          if (it == 1 && signaller) mbar_arrive_cluster(rbars + 8 * BAR_LFREE);
          s4();
        }
        if (it < 2) s1(it + 2);
        if (w == 0) PROF3(40 + 4 * wg + it);
      }
      if (MODE == 0) {
        mbar_wait(bars + 8 * BAR_FULL2, 0);
        g2_step(0, 0);
        wg_wait<1>();
      } else {
        wg_wait<0>();
      }
      if (signaller) mbar_arrive_cluster(rbars + 8 * (BAR_EMPTY2 + 4));
      e4(1);
      if (MODE == 0) {
        wg_wait<0>();
        if (signaller) mbar_arrive_cluster(rbars + 8 * BAR_EMPTY2);
      }
      PROF(6 + wg);
    }
    }

    if (MODE != 1) {
      int s = MODE == 0, ph = 0;
#pragma unroll 1
      for (int kb = s; kb < STAG; kb++) {
        mbar_wait(bars + 8 * (BAR_FULL2 + s), ph);
        if (kb == 1) PROF(8 + wg);
        if (warp == 4) PROF2(40 + kb);
        g2_step(s, kb);
        wg_wait<0>();
        if (kb < 16 - NS2 && signaller) mbar_arrive_cluster(rbars + 8 * (BAR_EMPTY2 + s));
        if (++s == NS2) { s = 0; ph ^= 1; }
      }
      {
        if (wg == 0) nb_sync(NB_LEAD, 256);
#pragma unroll
        for (int kb = STAG; kb < 16; kb++) {
          mbar_wait(bars + 8 * (BAR_FULL2 + kb % NS2), (kb / NS2) & 1);
          g2_step(kb % NS2, 1);
        }
        if (wg == 1) nb_arrive(NB_LEAD, 256);
      }
      wg_wait<0>();
      fence_regs(acc);
      PROF(10 + wg);
      const int lr = lane & 7, lm = lane >> 3;
      const uint32_t wbase = sb + warp * 2048;
      const uint32_t base = wbase + (lr + 8 * (lm & 1)) * 128;
#pragma unroll
      for (int j = 0; j < 16; j += 2) {
        const uint32_t a = base + (j >> 3) * 16384 + ((((j & 7) + (lm >> 1)) ^ lr) << 4);
        stsm4(a, pack_bf16(acc[4 * j], acc[4 * j + 1]), pack_bf16(acc[4 * j + 2], acc[4 * j + 3]),
              pack_bf16(acc[4 * j + 4], acc[4 * j + 5]), pack_bf16(acc[4 * j + 6], acc[4 * j + 7]));
      }
      __syncwarp();
      {
        const int rr = lane >> 4, ck = lane & 7, hf = (lane >> 3) & 1;
        uint4* og = reinterpret_cast<uint4*>(p.out + (size_t)(2 * ((rb2 & 7) * 128 + warp * 16 + rr) + (rb2 >> 3)) * (2 * DM) + DM + cb2 * 128 + hf * 64 + ck * 8);
        uint4 v[8];
#pragma unroll
        for (int i = 0; i < 8; i++) v[i] = lds128(wbase + hf * 16384 + (2 * i + rr) * 128 + ((ck ^ ((2 * i + rr) & 7)) << 4));
#pragma unroll
        for (int i = 0; i < 8; i++) og[(size_t)i * 4 * (2 * DM / 8)] = v[i];
      }
      PROF(12 + wg);
    }
    cluster_sync_all();
  }
}

typedef CUresult (*EncodeFn)(CUtensorMap*, CUtensorMapDataType, cuuint32_t, void*, const cuuint64_t*, const cuuint64_t*,
                             const cuuint32_t*, const cuuint32_t*, CUtensorMapInterleave, CUtensorMapSwizzle,
                             CUtensorMapL2promotion, CUtensorMapFloatOOBfill);

void make_map(EncodeFn enc, CUtensorMap* tm, const void* base, int rank, const cuuint64_t* dims, const cuuint64_t* strides,
              const cuuint32_t* box, CUtensorMapSwizzle swz) {
  cuuint32_t es[5] = {1, 1, 1, 1, 1};
  enc(tm, CU_TENSOR_MAP_DATA_TYPE_BFLOAT16, rank, const_cast<void*>(base), dims, strides, box, es,
      CU_TENSOR_MAP_INTERLEAVE_NONE, swz, CU_TENSOR_MAP_L2_PROMOTION_L2_256B, CU_TENSOR_MAP_FLOAT_OOB_FILL_NONE);
}

}

extern "C" void kernel_launch(void* const* d_in, const int* in_sizes, int n_in, void* d_out, int out_size) {
  static EncodeFn enc = nullptr;
  static bool coresident = true;
  if (!enc) {
    void* fn = nullptr;
    cudaDriverEntryPointQueryResult qr;
    cudaGetDriverEntryPoint("cuTensorMapEncodeTiled", &fn, cudaEnableDefault, &qr);
    enc = (EncodeFn)fn;
    cudaFuncSetAttribute(fused_kernel<0>, cudaFuncAttributeMaxDynamicSharedMemorySize, SMEM_BYTES);
    cudaFuncSetAttribute(fused_kernel<1>, cudaFuncAttributeMaxDynamicSharedMemorySize, SMEM_BYTES);
    cudaFuncSetAttribute(fused_kernel<2>, cudaFuncAttributeMaxDynamicSharedMemorySize, SMEM_BYTES);
    cudaLaunchConfig_t cfg = {};
    cfg.gridDim = dim3(NCTA);
    cfg.blockDim = dim3(NTHREADS);
    cfg.dynamicSmemBytes = SMEM_BYTES;
    cudaLaunchAttribute at;
    at.id = cudaLaunchAttributeClusterDimension;
    at.val.clusterDim.x = 2;
    at.val.clusterDim.y = 1;
    at.val.clusterDim.z = 1;
    cfg.attrs = &at;
    cfg.numAttrs = 1;
    int nclusters = 0;
    if (cudaOccupancyMaxActiveClusters(&nclusters, fused_kernel<0>, &cfg) == cudaSuccess) coresident = nclusters >= NCTA / 2;
    (void)cudaGetLastError();
  }
  CUtensorMap tmX, tmW, tmWo, tmQ, tmXh, tmWh;
  {
    cuuint64_t dims[3] = {1024, 2, 1024};
    cuuint64_t str[2] = {2048, 4096};
    cuuint32_t box[3] = {64, 1, 128};
    make_map(enc, &tmX, d_in[6], 3, dims, str, box, CU_TENSOR_MAP_SWIZZLE_128B);
  }
  {
    cuuint64_t dims[3] = {1024, 1024, 3};
    cuuint64_t str[2] = {6144, 2048};
    cuuint32_t box[3] = {64, 32, 3};
    make_map(enc, &tmW, d_in[7], 3, dims, str, box, CU_TENSOR_MAP_SWIZZLE_128B);
  }
  {
    cuuint64_t dims[3] = {64, 1024, 16};
    cuuint64_t str[2] = {2048, 128};
    cuuint32_t box[3] = {64, 64, 2};
    make_map(enc, &tmWo, d_in[8], 3, dims, str, box, CU_TENSOR_MAP_SWIZZLE_128B);
  }
  {
    cuuint64_t dims[5] = {1024, 2, 2, 8, 64};
    cuuint64_t str[4] = {2048, 16 * 2048, 2 * 2048, 32 * 2048};
    cuuint32_t box[5] = {16, 2, 2, 8, 4};
    make_map(enc, &tmQ, d_in[0], 5, dims, str, box, CU_TENSOR_MAP_SWIZZLE_NONE);
  }
  {
    cuuint64_t dims[4] = {1024, 256, 2, 4};
    cuuint64_t str[3] = {4096, 2048, 256 * 4096};
    cuuint32_t box[4] = {64, 8, 2, 4};
    make_map(enc, &tmXh, d_in[6], 4, dims, str, box, CU_TENSOR_MAP_SWIZZLE_128B);
  }
  {
    cuuint64_t dims[3] = {64, 1024, 48};
    cuuint64_t str[2] = {6144, 128};
    cuuint32_t box[3] = {64, 64, 4};
    make_map(enc, &tmWh, d_in[7], 3, dims, str, box, CU_TENSOR_MAP_SWIZZLE_128B);
  }
  Params p;
  p.q = (const __nv_bfloat16*)d_in[0];
  p.k = (const __nv_bfloat16*)d_in[1];
  p.v = (const __nv_bfloat16*)d_in[2];
  p.shift_k = (const __nv_bfloat16*)d_in[3];
  p.ssm_k = (const __nv_bfloat16*)d_in[4];
  p.ssm_D = (const __nv_bfloat16*)d_in[5];
  p.x = (const __nv_bfloat16*)d_in[6];
  p.w = (const __nv_bfloat16*)d_in[7];
  p.wo = (const __nv_bfloat16*)d_in[8];
  p.out = (__nv_bfloat16*)d_out;
  if (coresident) {
    fused_kernel<0><<<NCTA, NTHREADS, SMEM_BYTES>>>(p, tmX, tmW, tmWo, tmQ, tmXh, tmWh);
  } else {
    fused_kernel<0><<<4, NTHREADS, SMEM_BYTES>>>(p, tmX, tmW, tmWo, tmQ, tmXh, tmWh);
    fused_kernel<1><<<NCTA, NTHREADS, SMEM_BYTES>>>(p, tmX, tmW, tmWo, tmQ, tmXh, tmWh);
    fused_kernel<2><<<NCTA, NTHREADS, SMEM_BYTES>>>(p, tmX, tmW, tmWo, tmQ, tmXh, tmWh);
  }
}
```

```cpp
#include <cuda_runtime.h>
#include <cuda.h>
#include <cuda_bf16.h>
#include <stdint.h>

namespace {

constexpr int SEQ = 2048;
constexpr int DM = 1024;
constexpr int NCTA = 132;
constexpr int NTHREADS = 384;

constexpr int STG1A = 32768;
constexpr int NS1A = 3;
constexpr int STG1B = 12288;
constexpr int NS1B = 5;
constexpr int OFF_1B = NS1A * STG1A;
constexpr int STG2 = 32768;
constexpr int NS2 = 5;
constexpr int STGH = 73728;
constexpr int OFF_VP = 0;
constexpr int OFF_OP = 1 * STG2;
constexpr int OFF_Q = 2 * STG2;
constexpr int T_A4 = 0, T_TW = 16384, T_B2 = 24576, T_A1 = 28672, T_END = 32768;
constexpr int OFF_U = 163840;
constexpr int OFF_H = OFF_U + 32768;
constexpr int OFF_T = OFF_U - T_END;
constexpr int OFF_LAND = 4 * STG2;
constexpr int OFF_BAR = OFF_H + 32768;
constexpr int OFF_SC = OFF_BAR + 512;
constexpr int HALO = 2048;
constexpr int SMEM_BYTES = HALO + OFF_BAR + 1024;
static_assert(OFF_T + T_A1 == OFF_1B + NS1B * STG1B && OFF_T + T_TW == OFF_1B + 4 * STG1B && OFF_LAND == OFF_T + T_A4, "layout");
static_assert(3 * STGH <= OFF_BAR && SMEM_BYTES <= 232448, "smem");

constexpr int BAR_FULLA = 0;
constexpr int BAR_EMPTYA = 3;
constexpr int BAR_FULLB = 6;
constexpr int BAR_EMPTYB = 11;
constexpr int BAR_FULL2 = 16;
constexpr int BAR_EMPTY2 = 21;
constexpr int BAR_T = 26;
constexpr int BAR_UH = 27;
constexpr int BAR_LFREE = 28;
constexpr int BAR_LAND = 29;
constexpr int BAR_U = 30;
constexpr int BAR_Q = 31;
constexpr int BAR_STG = 32;
constexpr int BAR_DEAD = 33;
constexpr int BAR_X = 35;
constexpr int BAR_REL = 36;

constexpr int NB_G1DONE = 1;
constexpr int NB_OREADY = 2;
constexpr int NB_WG = 4;
constexpr int NB_HELP3 = 6;
constexpr int NB_FIRST = 7;
constexpr int NB_LEAD = 8;

#define PDELAY 400
constexpr int REG_MATH = 224, REG_HELP = 56;
constexpr int PF0 = 20;
constexpr uint32_t PACE = 390;
constexpr int STAG = 12;
constexpr int SPIN_LIMIT = 1 << 20;

__device__ __align__(1024) __nv_bfloat16 g_o[SEQ * DM];
__device__ __align__(128) uint32_t g_flag_o[256];
__device__ uint32_t g_flag_h[4];
__device__ uint4 g_halo[128 * 128];
__device__ __align__(128) const uint32_t g_tab[T_END / 4] = {
0x4a3a49fd,0x4acb4a1e,0x4906494e,0x48394928,0x4aa94a73,0x4bb74b55,0x486e48bb,0x443b4668,0x4b0a4adc,0x4c004bf0,0x4799481e,0xb54d3fe2,
0x4b5c4b35,0x4b9f4be4,0x464546f1,0xc4dec141,0x4b434a3e,0x4b9e4a5d,0x46b84901,0x44e448d9,0x4bfd4bdb,0x4b754bff,0xba934213,0xc5cbb7a8,
0x4ae14ba8,0x47f14a10,0xc816c4a2,0xcaf2c939,0x482e49b2,0xc12841b0,0xcad2c99e,0xcbe5cbdf,0x4bdc4a7b,0x4bfc4a98,0x41fa48b1,0x3c2b4888,
0x4a2c4bc0,0x48444b20,0xc917c3f1,0xcac5c745,0x2bdb46da,0xc7d5367b,0xcc00cb3b,0xcafacbff,0xca22c6be,0xcc00caef,0xc923cb41,0x3376c7fb,
0x4bfd4ab4,0x4bdf4acf,0xbb5c485e,0xc1bd4834,0x43b44a28,0xbcdb48e3,0xcbc4c91c,0xcbfaca55,0xcad9c61d,0xcbffc9ca,0xc824cb65,0xb744c985,
0xc9fbcbf7,0xc03cca18,0x49503dd5,0x4bee492f,0x4ba34ae9,0x4b494b01,0xc4c64809,0xc69b47ba,0xc62846c3,0xc93d42d8,0xcb62cb40,0xca0ccbd1,
0xcb12cb88,0xc84ecbfb,0x477dc567,0x4abe3ca9,0x4861c3fd,0x4bb045a8,0x4ab24bbf,0x446c4b7c,0x4ad44b19,0x4a444b30,0xc82c4761,0xc8fa4707,
0xcadfad7f,0xcbcfc32e,0xc819cc00,0xc2f0cbcc,0xbac5cb0f,0x4724c8ed,0x4bfd4788,0x4b294a4e,0x4b444a9f,0x46a14c00,0xc6b2487e,0xcb48b484,
0x499c4b45,0x48de4b5a,0xc9b446ad,0xca594651,0xcbf6c6eb,0xcb4ec8f5,0x3e6bcb37,0x4684ca48,0x4aa2c3cd,0x4bfa4172,0x48784bc2,0x3cf44be2,
0xc47e4a75,0xcab74520,0xcbaec8b9,0xc859cb94,0x480e4b6d,0x465c4b7f,0xcae545f4,0xcb574596,0xc9eaca36,0xc7dbcb2a,0x4963c90b,0x4af8c71e,
0x4b3f4871,0x48a24ac1,0xc6c94aa8,0xca864849,0xcbedc48a,0xc949ca46,0x4061cbac,0x4a01c8f7,0x44844b90,0x41344ba0,0xcbad4537,0xcbe544d8,
0xc22ccbc5,0x3ffbcc00,0x4bdac39c,0x4bf0b4e9,0x3e844bea,0xc66d4bb6,0xcbf540b8,0xcb53c441,0xb11bcbfd,0x492acaca,0x4c00bb2a,0x4a1c483c,
0x39344baf,0xbd3f4bbc,0xcbfe4478,0xcbf94417,0x46e0cbd6,0x4988cb4c,0x4b394269,0x49c84690,0xca684a30,0xcbf04734,0xc8cac912,0xc00acb25,
0x4be7c63a,0x4acd42cc,0x41034b5f,0xc8364bd1,0xc2824bc8,0xc5264bd3,0xcbd5436b,0xcb9342a7,0x4b10ca66,0x4be3c931,0x478348cd,0x41664a16,
0xcb673a61,0xc8f2c5bf,0x4611cbfd,0x4a4acb77,0x44cc49e4,0xc6564bef,0xcba2496a,0xcb584023,0xc6f64bdd,0xc8564be6,0xcb3441e2,0xcab9411c,
0x4be9c777,0x4b23c42f,0xc0c54b13,0xc73a4bb9,0xc0d1c9a7,0x45b3cb76,0x4be9c9a9,0x4b7ac5c5,0xcb334b15,0xcbbb474b,0xc6fcc772,0x441dcb1f,
0xc9214bed,0xc9d74bf3,0xca244055,0xc9783f1a,0x49a5b998,0x472941a4,0xc9ab4bfe,0xcb274be0,0x4a2acbfe,0x4be0cb26,0x49193a2f,0x4197472f,
0xc883c07a,0x3f33c97a,0x4a9bcbec,0x4bf3c9d5,0xca774bf8,0xcafe4bfc,0xc8b63d8a,0xc7c53bf2,0x409f4634,0xc18b48a4,0xcbeb4b60,0xcbe14a84,
0x4b8bc914,0x4940c447,0xc5554a2e,0xca0a4bb5,0x49e0cbd6,0x4bffcb56,0x496ec276,0x386b4662,0xcb6b4bff,0xcbba4c00,0xc5ff38cf,0xc42332ad,
0xc79349f5,0xc9cf4afb,0xcb0c4957,0xc98147d0,0x425d40ac,0xc4f64846,0xcbd74bea,0xcb9b4ac3,0x4a3cc829,0x41c93c44,0xc9034ad5,0xcbde4bfb,
0xcbec4c00,0xcc004bff,0xc06eb1e4,0xb420b89d,0xcb3d4bab,0xcbf14bfb,0xc6cf4490,0xbfb03c5e,0xc9e84aa6,0xcbcd4be2,0xc9654873,0xc322417f,
0xc80b4908,0xcb924bb2,0xcae74a38,0xc52c4460,0xcbf44bfc,0xcbca4bf9,0x3ecfbbc0,0x4346bd71,0xcbd84be8,0xcaf44b73,0x4251c0de,0x47ebc5d7,
0xcbaa4bc3,0xc98a4a4f,0x4496c3c0,0x49c6c8eb,0xcb6c4b8d,0xc75648a7,0x45fac549,0x4b1cca82,0xcb824bf4,0xcb1d4bee,0x4584bf01,0x4750c048,
0xc95c4aa1,0xc673497c,0x49f1c87b,0x4b52c9d3,0xc3e5478e,0x44353cc2,0x4bc1cb0d,0x4bb8cbfa,0x43772f12,0x4a7fc890,0x4bc7cc00,0x48acca93,
0xca9d4be6,0xca034bde,0x4880c10f,0x4947c1d5,0xbe204813,0x431544f0,0x4bf7cae2,0x4bcdcb9c,0x49a3c561,0x4bb4c983,0x49aecb89,0x4454c9cc,
0x4bf8cb83,0x4993cbba,0xbda3c57e,0xc9bd4429,0xc9534bd4,0xc88d4bc9,0x49f9c29b,0x4a94c35f,0x48213dee,0x4a12c016,0x4adacbf7,0x4936cbef,
0x4bc5cb64,0x49d1cbff,0xc3a8c622,0xc97e3616,0x3b8ec91e,0xc8dcbd26,0xcbfc4a26,0xca5b4bf9,0xc76c4bbd,0xc5a24baf,0x4b16c411,0x4b7dc472,
0x4b66c579,0x4bfbc851,0x4617cb85,0x3c90cabc,0x44b4cb3c,0xc2e4c93b,0xcba646d4,0xcbd04a0e,0xcbd54811,0xcb004b4b,0xc28e4ae4,0x47bf4696,
0xc3834ba1,0xbf4c4b91,0x4bc7c4d2,0x4bf3c531,0x4bc1c9b0,0x4ac0cac8,0xc3d9c9a0,0xc84cc83e,0xc95ac4a8,0xcb963fc9,0xc9f34ba7,0xc5144bf1,
0xc58a4bdb,0x459c498e,0x4b81c207,0x4b7ec9c1,0x30524b80,0x402f4b6e,0x4c00c590,0x4beec5ee,0x4910cb8c,0x45b9cbf2,0xca32c54f,0xcb78bf7e,
0xcbda481c,0xca144a8a,0x421f4add,0x4934489d,0x4b0440ea,0x4bd3c718,0x47afcbe8,0xc2b3cb2c,0x44054b5b,0x45e24b47,0x4bbec64b,0x4b70c6a7,
0x39fdcbf5,0xc44ecb95,0xcbfe3e9d,0xcbb5451a,0xc5734bd8,0x415a4bcf,0x4b864244,0x4be3c2fd,0x48d4cb07,0xbc12cbf2,0xca61c7a4,0xcbfc3f65,
0x47a94b31,0x48a94b1b,0x4b06c702,0x4a80c75c,0xc876cad7,0xca51c9c4,0xcaa44826,0xc8e8498c,0x490d4a6e,0x4b7447e6,0x4a34c8c3,0x45d1caf5,
0xc99ac9f7,0xcbf9c33a,0xc9b74955,0xbd584bcb,0x496c4b03,0x4a1a4aea,0x49e2c7b4,0x492dc806,0xcb8ac869,0xcbffc5ae,0xc55b4aad,0xb5b24b7b,
0x4beb3e52,0x4a53c502,0xc093cbf6,0xc8e6cb99,0xca794605,0xc3524abb,0x48b44b69,0x4bca4854,0x4ab04ad0,0x4b2d4ab6,0x4863c831,0x4713c85c,
0xcba6c086,0xca883d0d,0x44ae4beb,0x489f4bfa,0x462ec95e,0xbf97cb50,0xcb61c9ef,0xcbf2c67f,0x47674bfe,0x4b6f4a57,0x4b18b966,0x45e8c8e1,
0x4b8e4a9a,0x4bd24a7d,0x4543c885,0x42bfc8ae,0xc8c044ba,0xc4fc47f6,0x4a704ba5,0x4b9a4af0,0xc8becc00,0xcb4dcb51,0xca72a248,0xc68a4679,
0x4b8f44c0,0x4803c4ea,0xc53dcba4,0xcaeccb9d,0x4bf84a5f,0x4bff4a40,0x3dbcc8d7,0xb839c8fe,0x28b64967,0x450e4a91,0x4c0049e6,0x4b974892,
0xcbf7c961,0xca8fc508,0x3e0749ec,0x48954b98,0xc1eeca65,0xca42cbff,0xcbddc8cf,0xc8fcb806,0x4be74a20,0x4bb149ff,0xc0f6c925,0xc466c94b,
0x48c84b68,0x4a8d4be4,0x4a6a460b,0x4897414d,0xc6e53e39,0x3c7747e0,0x4b384bf6,0x4bfb4af7,0xcbfecaaf,0xc9d9c5dc,0x39014866,0x49754b72,
0x4b5d49de,0x4aed49bb,0xc63fc971,0xc800c995,0x4ba94bfd,0x4bff4bb3,0x449cbaf8,0xb6dfc45a,0x486b4a6c,0x4b224bce,0x4aab48c5,0x47404309,
0xbee84390,0x488b4a05,0x4bf44bc6,0x4a964944,0x4a634997,0x49bf4973,0xc8d2c9b9,0xc991c9db,0x4b874b09,0x4a4c4a08,0xc56dc79e,0xc8f0c942,
0x4bfe4bd9,0x4ac64a8b,0xb9cac238,0xc841c89a,0x4bbe4bf5,0x4b2e4afd,0x440b3eb6,0xc70dc7ca,0x4a3a49fd,0xcacbca1e,0x4906494e,0xc839c928,
0x4aa94a73,0xcbb7cb55,0x486e48bb,0xc43bc668,0x4b0a4adc,0xcc00cbf0,0x4799481e,0x354dbfe2,0x4b5c4b35,0xcb9fcbe4,0x464546f1,0x44de4141,
0x4b434a3e,0xcb9eca5d,0x46b84901,0xc4e4c8d9,0x4bfd4bdb,0xcb75cbff,0xba934213,0x45cb37a8,0x4ae14ba8,0xc7f1ca10,0xc816c4a2,0x4af24939,
0x482e49b2,0x4128c1b0,0xcad2c99e,0x4be54bdf,0x4bdc4a7b,0xcbfcca98,0x41fa48b1,0xbc2bc888,0x4a2c4bc0,0xc844cb20,0xc917c3f1,0x4ac54745,
0x2bdb46da,0x47d5b67b,0xcc00cb3b,0x4afa4bff,0xca22c6be,0x4c004aef,0xc923cb41,0xb37647fb,0x4bfd4ab4,0xcbdfcacf,0xbb5c485e,0x41bdc834,
0x43b44a28,0x3cdbc8e3,0xcbc4c91c,0x4bfa4a55,0xcad9c61d,0x4bff49ca,0xc824cb65,0x37444985,0xc9fbcbf7,0x403c4a18,0x49503dd5,0xcbeec92f,
0x4ba34ae9,0xcb49cb01,0xc4c64809,0x469bc7ba,0xc62846c3,0x493dc2d8,0xcb62cb40,0x4a0c4bd1,0xcb12cb88,0x484e4bfb,0x477dc567,0xcabebca9,
0x4861c3fd,0xcbb0c5a8,0x4ab24bbf,0xc46ccb7c,0x4ad44b19,0xca44cb30,0xc82c4761,0x48fac707,0xcadfad7f,0x4bcf432e,0xc819cc00,0x42f04bcc,
0xbac5cb0f,0xc72448ed,0x4bfd4788,0xcb29ca4e,0x4b444a9f,0xc6a1cc00,0xc6b2487e,0x4b483484,0x499c4b45,0xc8decb5a,0xc9b446ad,0x4a59c651,
0xcbf6c6eb,0x4b4e48f5,0x3e6bcb37,0xc6844a48,0x4aa2c3cd,0xcbfac172,0x48784bc2,0xbcf4cbe2,0xc47e4a75,0x4ab7c520,0xcbaec8b9,0x48594b94,
0x480e4b6d,0xc65ccb7f,0xcae545f4,0x4b57c596,0xc9eaca36,0x47db4b2a,0x4963c90b,0xcaf8471e,0x4b3f4871,0xc8a2cac1,0xc6c94aa8,0x4a86c849,
0xcbedc48a,0x49494a46,0x4061cbac,0xca0148f7,0x44844b90,0xc134cba0,0xcbad4537,0x4be5c4d8,0xc22ccbc5,0xbffb4c00,0x4bdac39c,0xcbf034e9,
0x3e844bea,0x466dcbb6,0xcbf540b8,0x4b534441,0xb11bcbfd,0xc92a4aca,0x4c00bb2a,0xca1cc83c,0x39344baf,0x3d3fcbbc,0xcbfe4478,0x4bf9c417,
0x46e0cbd6,0xc9884b4c,0x4b394269,0xc9c8c690,0xca684a30,0x4bf0c734,0xc8cac912,0x400a4b25,0x4be7c63a,0xcacdc2cc,0x41034b5f,0x4836cbd1,
0xc2824bc8,0x4526cbd3,0xcbd5436b,0x4b93c2a7,0x4b10ca66,0xcbe34931,0x478348cd,0xc166ca16,0xcb673a61,0x48f245bf,0x4611cbfd,0xca4a4b77,
0x44cc49e4,0x4656cbef,0xcba2496a,0x4b58c023,0xc6f64bdd,0x4856cbe6,0xcb3441e2,0x4ab9c11c,0x4be9c777,0xcb23442f,0xc0c54b13,0x473acbb9,
0xc0d1c9a7,0xc5b34b76,0x4be9c9a9,0xcb7a45c5,0xcb334b15,0x4bbbc74b,0xc6fcc772,0xc41d4b1f,0xc9214bed,0x49d7cbf3,0xca244055,0x4978bf1a,
0x49a5b998,0xc729c1a4,0xc9ab4bfe,0x4b27cbe0,0x4a2acbfe,0xcbe04b26,0x49193a2f,0xc197c72f,0xc883c07a,0xbf33497a,0x4a9bcbec,0xcbf349d5,
0xca774bf8,0x4afecbfc,0xc8b63d8a,0x47c5bbf2,0x409f4634,0x418bc8a4,0xcbeb4b60,0x4be1ca84,0x4b8bc914,0xc9404447,0xc5554a2e,0x4a0acbb5,
0x49e0cbd6,0xcbff4b56,0x496ec276,0xb86bc662,0xcb6b4bff,0x4bbacc00,0xc5ff38cf,0x4423b2ad,0xc79349f5,0x49cfcafb,0xcb0c4957,0x4981c7d0,
0x425d40ac,0x44f6c846,0xcbd74bea,0x4b9bcac3,0x4a3cc829,0xc1c9bc44,0xc9034ad5,0x4bdecbfb,0xcbec4c00,0x4c00cbff,0xc06eb1e4,0x3420389d,
0xcb3d4bab,0x4bf1cbfb,0xc6cf4490,0x3fb0bc5e,0xc9e84aa6,0x4bcdcbe2,0xc9654873,0x4322c17f,0xc80b4908,0x4b92cbb2,0xcae74a38,0x452cc460,
0xcbf44bfc,0x4bcacbf9,0x3ecfbbc0,0xc3463d71,0xcbd84be8,0x4af4cb73,0x4251c0de,0xc7eb45d7,0xcbaa4bc3,0x498aca4f,0x4496c3c0,0xc9c648eb,
0xcb6c4b8d,0x4756c8a7,0x45fac549,0xcb1c4a82,0xcb824bf4,0x4b1dcbee,0x4584bf01,0xc7504048,0xc95c4aa1,0x4673c97c,0x49f1c87b,0xcb5249d3,
0xc3e5478e,0xc435bcc2,0x4bc1cb0d,0xcbb84bfa,0x43772f12,0xca7f4890,0x4bc7cc00,0xc8ac4a93,0xca9d4be6,0x4a03cbde,0x4880c10f,0xc94741d5,
0xbe204813,0xc315c4f0,0x4bf7cae2,0xcbcd4b9c,0x49a3c561,0xcbb44983,0x49aecb89,0xc45449cc,0x4bf8cb83,0xc9934bba,0xbda3c57e,0x49bdc429,
0xc9534bd4,0x488dcbc9,0x49f9c29b,0xca94435f,0x48213dee,0xca124016,0x4adacbf7,0xc9364bef,0x4bc5cb64,0xc9d14bff,0xc3a8c622,0x497eb616,
0x3b8ec91e,0x48dc3d26,0xcbfc4a26,0x4a5bcbf9,0xc76c4bbd,0x45a2cbaf,0x4b16c411,0xcb7d4472,0x4b66c579,0xcbfb4851,0x4617cb85,0xbc904abc,
0x44b4cb3c,0x42e4493b,0xcba646d4,0x4bd0ca0e,0xcbd54811,0x4b00cb4b,0xc28e4ae4,0xc7bfc696,0xc3834ba1,0x3f4ccb91,0x4bc7c4d2,0xcbf34531,
0x4bc1c9b0,0xcac04ac8,0xc3d9c9a0,0x484c483e,0xc95ac4a8,0x4b96bfc9,0xc9f34ba7,0x4514cbf1,0xc58a4bdb,0xc59cc98e,0x4b81c207,0xcb7e49c1,
0x30524b80,0xc02fcb6e,0x4c00c590,0xcbee45ee,0x4910cb8c,0xc5b94bf2,0xca32c54f,0x4b783f7e,0xcbda481c,0x4a14ca8a,0x421f4add,0xc934c89d,
0x4b0440ea,0xcbd34718,0x47afcbe8,0x42b34b2c,0x44054b5b,0xc5e2cb47,0x4bbec64b,0xcb7046a7,0x39fdcbf5,0x444e4b95,0xcbfe3e9d,0x4bb5c51a,
0xc5734bd8,0xc15acbcf,0x4b864244,0xcbe342fd,0x48d4cb07,0x3c124bf2,0xca61c7a4,0x4bfcbf65,0x47a94b31,0xc8a9cb1b,0x4b06c702,0xca80475c,
0xc876cad7,0x4a5149c4,0xcaa44826,0x48e8c98c,0x490d4a6e,0xcb74c7e6,0x4a34c8c3,0xc5d14af5,0xc99ac9f7,0x4bf9433a,0xc9b74955,0x3d58cbcb,
0x496c4b03,0xca1acaea,0x49e2c7b4,0xc92d4806,0xcb8ac869,0x4bff45ae,0xc55b4aad,0x35b2cb7b,0x4beb3e52,0xca534502,0xc093cbf6,0x48e64b99,
0xca794605,0x4352cabb,0x48b44b69,0xcbcac854,0x4ab04ad0,0xcb2dcab6,0x4863c831,0xc713485c,0xcba6c086,0x4a88bd0d,0x44ae4beb,0xc89fcbfa,
0x462ec95e,0x3f974b50,0xcb61c9ef,0x4bf2467f,0x47674bfe,0xcb6fca57,0x4b18b966,0xc5e848e1,0x4b8e4a9a,0xcbd2ca7d,0x4543c885,0xc2bf48ae,
0xc8c044ba,0x44fcc7f6,0x4a704ba5,0xcb9acaf0,0xc8becc00,0x4b4d4b51,0xca72a248,0x468ac679,0x4b8f44c0,0xc80344ea,0xc53dcba4,0x4aec4b9d,
0x4bf84a5f,0xcbffca40,0x3dbcc8d7,0x383948fe,0x28b64967,0xc50eca91,0x4c0049e6,0xcb97c892,0xcbf7c961,0x4a8f4508,0x3e0749ec,0xc895cb98,
0xc1eeca65,0x4a424bff,0xcbddc8cf,0x48fc3806,0x4be74a20,0xcbb1c9ff,0xc0f6c925,0x4466494b,0x48c84b68,0xca8dcbe4,0x4a6a460b,0xc897c14d,
0xc6e53e39,0xbc77c7e0,0x4b384bf6,0xcbfbcaf7,0xcbfecaaf,0x49d945dc,0x39014866,0xc975cb72,0x4b5d49de,0xcaedc9bb,0xc63fc971,0x48004995,
0x4ba94bfd,0xcbffcbb3,0x449cbaf8,0x36df445a,0x486b4a6c,0xcb22cbce,0x4aab48c5,0xc740c309,0xbee84390,0xc88bca05,0x4bf44bc6,0xca96c944,
0x4a634997,0xc9bfc973,0xc8d2c9b9,0x499149db,0x4b874b09,0xca4cca08,0xc56dc79e,0x48f04942,0x4bfe4bd9,0xcac6ca8b,0xb9cac238,0x4841489a,
0x4bbe4bf5,0xcb2ecafd,0x440b3eb6,0x470d47ca,0x4b9e4b7f,0x4a9d4b31,0x44e44596,0xc880c702,0x4bcf4bb9,0x491049e6,0x42f0442f,0xca32c967,
0x4bf04be2,0x462e481e,0x400a417f,0xcb61cadc,0x4bff4bf9,0x3ee843fd,0x386b3d26,0xcbf4cbbf,0x3c2b44d8,0xc9f9c7b4,0xcbfccba0,0xc953cb03,
0xc684c1a4,0xcbfecb68,0xcb4ecbe0,0xb9fdc60b,0xca4ac8eb,0xca72cba8,0xc8f2ca4f,0x48be44a2,0xcbdecb4b,0xc40bc87e,0xc1c9c696,0x4bbe4a9f,
0xcbdfcbbc,0xc76ccad0,0x41bdc417,0x4b164831,0xc7dbca84,0x48763af8,0x4af848a4,0x4aa44bfd,0x45b3bcc2,0x4bf74b3b,0x4b7a4bfa,0xbe0746da,
0x4b9249c1,0x46454a75,0x452c498e,0xcb5cc8b9,0x469bc2a7,0x4bc74885,0x4b494bd3,0x43834a9a,0x4bf04afb,0x455b4b09,0xbffb47d0,0xcb8ac79e,
0x419749cc,0xcb38c61d,0xcbe0c983,0xc6e5cb65,0xcb1cc718,0xc82ecbac,0xc756cb2c,0x4ad2448a,0x4a444be6,0xb0524a5f,0xc8fa411c,0xcc00c8d7,
0xc9883c5e,0xcba6ca73,0xc9c8cbfb,0x44aec8bb,0xc940cbff,0x486bc567,0x4a0a3616,0x4aab4b88,0x4a7f3f65,0x49234bfd,0x48ac4bf2,0xca223b2a,
0xca593f1a,0xcbbec925,0xc8decbf3,0x4405ca20,0xc166cb73,0x4a70c213,0x4be345d7,0x48c04bdb,0x4b9b4a0e,0xb9ca4b0f,0xc4f6493b,0xcbfec788,
0xc9bd433a,0xc9fbcb5f,0xc993cbcb,0x4950c63a,0xc65ccbfc,0x47a9c9de,0x4b57bbf2,0x4b064971,0x4b2349d3,0xa8b64bc0,0xc73a497c,0xcc00c3f1,
0xcbcdbfc9,0xc799cbc2,0xc322cbf1,0x4b0ac3cd,0x48dcc854,0x4ab249e4,0x4a5b4abb,0xc861496a,0x4be5b2ad,0x49e249b9,0x41344c00,0xc96c4997,
0xcb2744f0,0xca6ac91c,0xc729cb9c,0x48c8ca28,0x49c6c89d,0x4ae14871,0x498a4a8a,0xc8164aa8,0xc7bf4a57,0xcb44c772,0xcb00c8e1,0x46b2cb15,
0xbd3f4bff,0xcab0494e,0xcbf9b89d,0xc863c9fd,0x418bcbef,0x4ba9c6c3,0x4be14016,0x449c4b40,0xc4354bcf,0xcc0040b8,0xcbb8c2fd,0xabdbcbea,
0x459ccb9d,0x4bae407a,0x4b7e44ea,0xc47e4bec,0xcb93bd71,0xc543ca3e,0x4526cbf9,0x4b8ec901,0x49814851,0xc56d4c00,0xc9cf4abc,0xcb87ad7f,
0xc454caf5,0x4ad9ca30,0x4bb4c7e6,0x48244912,0xc2b34bff,0xcbed4276,0xcbd33806,0x4061cbd6,0x4856cbee,0x4bf8c8b1,0x4ab94048,0x3dbc4a7b,
0xcbf1483e,0xc86ec6eb,0xbfb0cac8,0x4aa9cb37,0x49d14502,0xc77d4bfd,0xc97e4b99,0xcb123a61,0x3c12cb72,0x4c00c829,0x4bfcc5dc,0x311b4ad5,
0x497841d5,0xc0f64ab4,0xc9d74bde,0xcbe7485e,0x47ebcbf2,0x4bfdc90b,0x4af4bf7e,0xba934a36,0xcbd0467f,0xbac5c9a7,0x42e4cb50,0x4bfdc9a9,
0x3d584a05,0xcbe74a38,0xcbf94944,0xc103c908,0xcafe4bc9,0xcb5d4809,0xc7c5c35f,0x463fcae9,0x4673451a,0xc9174bc5,0xcb524b95,0xca2c439c,
0x4b96cb51,0x48783a2f,0x45144679,0xcaa24bfe,0xc352c7ca,0x4ba2cb8d,0x4bcacafd,0x44cc4549,0xc423c472,0x48d2cb19,0x4bbacbaf,0x4a63c761,
0xcbcd49c4,0xc3b4c269,0x4315c98c,0x4bc4cbd6,0xc9344b98,0xcb3f4914,0xca144508,0x46c9ca2e,0x45e84141,0xcb334c00,0xcb6f4be4,0xc6fc2f12,
0x4c00cb91,0x4906c6ad,0x34204531,0xca3a4b45,0x4a12cb7b,0x4b62ca66,0x4936c5ae,0xc62848cd,0x415ac7e0,0x4bf5cbea,0x4be3caf7,0x3e8440ac,
0xc80341b0,0x4a9bcb83,0x4aeccbdf,0x4883c57e,0xc34645ee,0xcb434b6d,0xcbca4b6e,0xc6b845f4,0x3c903d0d,0xcadf4b13,0xcbfb4bfa,0xc8194777,
0x45d1c309,0xca684aa6,0xcb744bce,0xc8ca4873,0x48fcc7fb,0xc9e04a26,0xca424aef,0xc96e491e,0xcb1d4b47,0xc1fa4537,0x4750c6a7,0x4bdccb90,
0xcac04af0,0x3e6b3998,0x484cc7f6,0x4bf6cbfe,0xca534a8b,0x4611c3c0,0x48e6c89a,0x4b67cbc3,0xc9d94a18,0x4903c811,0x4975c92f,0x4a3ccae4,
0x4947c75c,0x4bfdcbaf,0x4a03cb1b,0xbb5cc478,0x4b78ca91,0x49eacb60,0x45b9c892,0xc9634634,0x4bf2cbf0,0x40d1c78e,0xbf97bfe2,0xcbe94b0d,
0x4a96cb7c,0xc80b4207,0xc88b45a8,0xcae74bdb,0x488dcaea,0xc4c6c36b,0xca944806,0xcba34bc8,0xc44ec14d,0xcbda49f5,0xcbb54be4,0xc22c4957,
0xcb4d4939,0xc9194b89,0xc68a4a10,0x4a2ac561,0xcb2e4c00,0x45fa40ea,0x470db484,0x4b6ccbe8,0xcb7d485c,0xcad44bdd,0xc5a24ab6,0x482c41e2,
0xc8e84bb3,0x46e04490,0x4a51c45a,0x4b39cbab,0x4895367b,0x4b8bcb64,0x4a8fcbff,0xc555c622,0x4b9fcb94,0xc377c7a4,0xc4dec520,0xcbc74b07,
0xbf4c4a7d,0x49b44055,0x4bf3c8ae,0x499ccbed,0x4bffc942,0x4783cbe8,0x35b2ca08,0xcb1040de,0xbc77c985,0xcbd746d4,0xcbfb49ca,0xc25d4b3c,
0xcbe54a46,0x3da349f7,0x412848f7,0x4bf8c955,0x4beec8fe,0x480ecbf8,0xc02fca40,0xcae5bd8a,0xc89fc668,0xcbe9487b,0xca884b55,0x40c54aa1,
0xc7404bfb,0x49e844a8,0x4b22bca9,0x4965cba7,0x4c00c83c,0x3b8ecb69,0xb376caca,0xcbfc4605,0xc5e2c9ff,0xcbadb8cf,0xcb70494b,0xc4844bff,
0xc4fc4bff,0x49ab4813,0x4b9ab7a8,0x49a5cae2,0x4ac6ca4e,0xc496cadd,0xc841c8ed,0xcbaa481c,0xcbee42cc,0xc28e4bfe,0xc03c4bd1,0x4bd5b966,
0xca804995,0xb9344c00,0x48a949bb,0x4bfeb1e4,0x4b97c745,0x409fcbf7,0xc50ecb20,0xcbebbdee,0xcc004172,0xc3e54bd8,0x354d4be2,0x4bc14244,
0x4bb04023,0x458acba4,0x446ccbef,0xcb81c4c0,0x4a1a4973,0x4bd5bbc0,0x492dc9db,0xc282cbfc,0xca8dc8e3,0xcb0c4579,0xc8974a55,0x47934b85,
0x4af24849,0x49aec8c3,0x47f1cac1,0xc9a3ca6e,0xcb48c74b,0xc7af4a65,0xc6a14b1f,0x4b0448cf,0x4713ca1e,0xc6f6cbf4,0xcb2dc928,0xcb343f01,
0x36df4bd1,0x4b3d49a0,0x4bff42d8,0x46cfc9b0,0xc7d5cbb6,0xcbc5be52,0xcafa4441,0x43a84bf6,0x4ab749d5,0x48d4c866,0x4859c97a,0xca61caaf,
0xcbd2c8d9,0xca24410f,0xc2bf4a5d,0x49214be6,0x4a4cc32e,0xc251cb8c,0xc8f0cbcc,0xcbd8c54f,0xb7444b25,0x4ba649ef,0x4bff4734,0x44b4c95e,
0xca01cb56,0xc9b74390,0xc9494662,0x499a4bc6,0x38394a98,0x4a774bd4,0x4bff4888,0x48b6c29b,0xcbb7ca48,0xc95c3e9d,0xc43b48f5,0x49f14bf5,
0x484ec5bf,0xc95acc00,0xcabecb77,0xc9f3a248,0x492a4bfb,0x4a793eb6,0x4a1cbc44,0xc8b4cbf5,0x4bb14834,0x45ffc411,0xc466cacf,0xcb6bcbbd,
0x45cb4b2a,0x4bf74ad7,0x4b75471e,0x3e20c826,0xcb29c5c5,0x421f49ec,0x47244b76,0x4bda4961,0xc836cbb2,0xcb18c6f1,0xcacdc460,0x47674b35,
0xc800cb01,0xcbeccba1,0xcaedc7ba,0xc06e44d2,0x484434e9,0xc821caad,0xcac5cc00,0xcadac869,0x4bfa4b26,0x4573be39,0x3cf4c72f,0xcb86cbf6,
0x46564a82,0x4b8f49b2,0x4b5848a7,0xc53dc99e,0xc9bfc707,0x3ecf4590,0x49914b30,0x4bf44b80,0xcbfacb4c,0xc617c086,0x3cdb4690,0x4b664beb,
0xca86cbb5,0xca34c8c5,0xc8a2c447,0x490d4a6c,0xc41dc890,0xcbddcb41,0xcbbbca93,0x41ee46be,0x4acb4b5a,0x4b824b5b,0x48394651,0xc584c64b,
0x493d4a16,0x4bc14ba5,0x4a0c4931,0xc3d9c4ba,0x466d4846,0x4beb4bd9,0x4b534ac3,0xc093c238,0x3f334429,0x4bfe4bf7,0x4bf34bba,0xb901bdd5,
0x4b9e4b7f,0xca9dcb31,0x44e44596,0x48804702,0x4bcf4bb9,0xc910c9e6,0x42f0442f,0x4a324967,0x4bf04be2,0xc62ec81e,0x400a417f,0x4b614adc,
0x4bff4bf9,0xbee8c3fd,0x386b3d26,0x4bf44bbf,0x3c2b44d8,0x49f947b4,0xcbfccba0,0x49534b03,0xc684c1a4,0x4bfe4b68,0xcb4ecbe0,0x39fd460b,
0xca4ac8eb,0x4a724ba8,0xc8f2ca4f,0xc8bec4a2,0xcbdecb4b,0x440b487e,0xc1c9c696,0xcbbeca9f,0xcbdfcbbc,0x476c4ad0,0x41bdc417,0xcb16c831,
0xc7dbca84,0xc876baf8,0x4af848a4,0xcaa4cbfd,0x45b3bcc2,0xcbf7cb3b,0x4b7a4bfa,0x3e07c6da,0x4b9249c1,0xc645ca75,0x452c498e,0x4b5c48b9,
0x469bc2a7,0xcbc7c885,0x4b494bd3,0xc383ca9a,0x4bf04afb,0xc55bcb09,0xbffb47d0,0x4b8a479e,0x419749cc,0x4b38461d,0xcbe0c983,0x46e54b65,
0xcb1cc718,0x482e4bac,0xc756cb2c,0xcad2c48a,0x4a444be6,0x3052ca5f,0xc8fa411c,0x4c0048d7,0xc9883c5e,0x4ba64a73,0xc9c8cbfb,0xc4ae48bb,
0xc940cbff,0xc86b4567,0x4a0a3616,0xcaabcb88,0x4a7f3f65,0xc923cbfd,0x48ac4bf2,0x4a22bb2a,0xca593f1a,0x4bbe4925,0xc8decbf3,0xc4054a20,
0xc166cb73,0xca704213,0x4be345d7,0xc8c0cbdb,0x4b9b4a0e,0x39cacb0f,0xc4f6493b,0x4bfe4788,0xc9bd433a,0x49fb4b5f,0xc993cbcb,0xc950463a,
0xc65ccbfc,0xc7a949de,0x4b57bbf2,0xcb06c971,0x4b2349d3,0x28b6cbc0,0xc73a497c,0x4c0043f1,0xcbcdbfc9,0x47994bc2,0xc322cbf1,0xcb0a43cd,
0x48dcc854,0xcab2c9e4,0x4a5b4abb,0x4861c96a,0x4be5b2ad,0xc9e2c9b9,0x41344c00,0x496cc997,0xcb2744f0,0x4a6a491c,0xc729cb9c,0xc8c84a28,
0x49c6c89d,0xcae1c871,0x498a4a8a,0x4816caa8,0xc7bf4a57,0x4b444772,0xcb00c8e1,0xc6b24b15,0xbd3f4bff,0x4ab0c94e,0xcbf9b89d,0x486349fd,
0x418bcbef,0xcba946c3,0x4be14016,0xc49ccb40,0xc4354bcf,0x4c00c0b8,0xcbb8c2fd,0x2bdb4bea,0x459ccb9d,0xcbaec07a,0x4b7e44ea,0x447ecbec,
0xcb93bd71,0x45434a3e,0x4526cbf9,0xcb8e4901,0x49814851,0x456dcc00,0xc9cf4abc,0x4b872d7f,0xc454caf5,0xcad94a30,0x4bb4c7e6,0xc824c912,
0xc2b34bff,0x4bedc276,0xcbd33806,0xc0614bd6,0x4856cbee,0xcbf848b1,0x4ab94048,0xbdbcca7b,0xcbf1483e,0x486e46eb,0xbfb0cac8,0xcaa94b37,
0x49d14502,0x477dcbfd,0xc97e4b99,0x4b12ba61,0x3c12cb72,0xcc004829,0x4bfcc5dc,0xb11bcad5,0x497841d5,0x40f6cab4,0xc9d74bde,0x4be7c85e,
0x47ebcbf2,0xcbfd490b,0x4af4bf7e,0x3a93ca36,0xcbd0467f,0x3ac549a7,0x42e4cb50,0xcbfd49a9,0x3d584a05,0x4be7ca38,0xcbf94944,0x41034908,
0xcafe4bc9,0x4b5dc809,0xc7c5c35f,0xc63f4ae9,0x4673451a,0x4917cbc5,0xcb524b95,0x4a2cc39c,0x4b96cb51,0xc878ba2f,0x45144679,0x4aa2cbfe,
0xc352c7ca,0xcba24b8d,0x4bcacafd,0xc4ccc549,0xc423c472,0xc8d24b19,0x4bbacbaf,0xca634761,0xcbcd49c4,0x43b44269,0x4315c98c,0xcbc44bd6,
0xc9344b98,0x4b3fc914,0xca144508,0xc6c94a2e,0x45e84141,0x4b33cc00,0xcb6f4be4,0x46fcaf12,0x4c00cb91,0xc90646ad,0x34204531,0x4a3acb45,
0x4a12cb7b,0xcb624a66,0x4936c5ae,0x4628c8cd,0x415ac7e0,0xcbf54bea,0x4be3caf7,0xbe84c0ac,0xc80341b0,0xca9b4b83,0x4aeccbdf,0xc883457e,
0xc34645ee,0x4b43cb6d,0xcbca4b6e,0x46b8c5f4,0x3c903d0d,0x4adfcb13,0xcbfb4bfa,0x4819c777,0x45d1c309,0x4a68caa6,0xcb744bce,0x48cac873,
0x48fcc7fb,0x49e0ca26,0xca424aef,0x496ec91e,0xcb1d4b47,0x41fac537,0x4750c6a7,0xcbdc4b90,0xcac04af0,0xbe6bb998,0x484cc7f6,0xcbf64bfe,
0xca534a8b,0xc61143c0,0x48e6c89a,0xcb674bc3,0xc9d94a18,0xc9034811,0x4975c92f,0xca3c4ae4,0x4947c75c,0xcbfd4baf,0x4a03cb1b,0x3b5c4478,
0x4b78ca91,0xc9ea4b60,0x45b9c892,0x4963c634,0x4bf2cbf0,0xc0d1478e,0xbf97bfe2,0x4be9cb0d,0x4a96cb7c,0x480bc207,0xc88b45a8,0x4ae7cbdb,
0x488dcaea,0x44c6436b,0xca944806,0x4ba3cbc8,0xc44ec14d,0x4bdac9f5,0xcbb54be4,0x422cc957,0xcb4d4939,0x4919cb89,0xc68a4a10,0xca2a4561,
0xcb2e4c00,0xc5fac0ea,0x470db484,0xcb6c4be8,0xcb7d485c,0x4ad4cbdd,0xc5a24ab6,0xc82cc1e2,0xc8e84bb3,0xc6e0c490,0x4a51c45a,0xcb394bab,
0x4895367b,0xcb8b4b64,0x4a8fcbff,0x45554622,0x4b9fcb94,0x437747a4,0xc4dec520,0x4bc7cb07,0xbf4c4a7d,0xc9b4c055,0x4bf3c8ae,0xc99c4bed,
0x4bffc942,0xc7834be8,0x35b2ca08,0x4b10c0de,0xbc77c985,0x4bd7c6d4,0xcbfb49ca,0x425dcb3c,0xcbe54a46,0xbda3c9f7,0x412848f7,0xcbf84955,
0x4beec8fe,0xc80e4bf8,0xc02fca40,0x4ae53d8a,0xc89fc668,0x4be9c87b,0xca884b55,0xc0c5caa1,0xc7404bfb,0xc9e8c4a8,0x4b22bca9,0xc9654ba7,
0x4c00c83c,0xbb8e4b69,0xb376caca,0x4bfcc605,0xc5e2c9ff,0x4bad38cf,0xcb70494b,0x4484cbff,0xc4fc4bff,0xc9abc813,0x4b9ab7a8,0xc9a54ae2,
0x4ac6ca4e,0x44964add,0xc841c8ed,0x4baac81c,0xcbee42cc,0x428ecbfe,0xc03c4bd1,0xcbd53966,0xca804995,0x3934cc00,0x48a949bb,0xcbfe31e4,
0x4b97c745,0xc09f4bf7,0xc50ecb20,0x4beb3dee,0xcc004172,0x43e5cbd8,0x354d4be2,0xcbc1c244,0x4bb04023,0xc58a4ba4,0x446ccbef,0x4b8144c0,
0x4a1a4973,0xcbd53bc0,0x492dc9db,0x42824bfc,0xca8dc8e3,0x4b0cc579,0xc8974a55,0xc793cb85,0x4af24849,0xc9ae48c3,0x47f1cac1,0x49a34a6e,
0xcb48c74b,0x47afca65,0xc6a14b1f,0xcb04c8cf,0x4713ca1e,0x46f64bf4,0xcb2dc928,0x4b34bf01,0x36df4bd1,0xcb3dc9a0,0x4bff42d8,0xc6cf49b0,
0xc7d5cbb6,0x4bc53e52,0xcafa4441,0xc3a8cbf6,0x4ab749d5,0xc8d44866,0x4859c97a,0x4a614aaf,0xcbd2c8d9,0x4a24c10f,0xc2bf4a5d,0xc921cbe6,
0x4a4cc32e,0x42514b8c,0xc8f0cbcc,0x4bd8454f,0xb7444b25,0xcba6c9ef,0x4bff4734,0xc4b4495e,0xca01cb56,0x49b7c390,0xc9494662,0xc99acbc6,
0x38394a98,0xca77cbd4,0x4bff4888,0xc8b6429b,0xcbb7ca48,0x495cbe9d,0xc43b48f5,0xc9f1cbf5,0x484ec5bf,0x495a4c00,0xcabecb77,0x49f32248,
0x492a4bfb,0xca79beb6,0x4a1cbc44,0x48b44bf5,0x4bb14834,0xc5ff4411,0xc466cacf,0x4b6b4bbd,0x45cb4b2a,0xcbf7cad7,0x4b75471e,0xbe204826,
0xcb29c5c5,0xc21fc9ec,0x47244b76,0xcbdac961,0xc836cbb2,0x4b1846f1,0xcacdc460,0xc767cb35,0xc800cb01,0x4bec4ba1,0xcaedc7ba,0x406ec4d2,
0x484434e9,0x48214aad,0xcac5cc00,0x4ada4869,0x4bfa4b26,0xc5733e39,0x3cf4c72f,0x4b864bf6,0x46564a82,0xcb8fc9b2,0x4b5848a7,0x453d499e,
0xc9bfc707,0xbecfc590,0x49914b30,0xcbf4cb80,0xcbfacb4c,0x46174086,0x3cdb4690,0xcb66cbeb,0xca86cbb5,0x4a3448c5,0xc8a2c447,0xc90dca6c,
0xc41dc890,0x4bdd4b41,0xcbbbca93,0xc1eec6be,0x4acb4b5a,0xcb82cb5b,0x48394651,0x4584464b,0x493d4a16,0xcbc1cba5,0x4a0c4931,0x43d944ba,
0x466d4846,0xcbebcbd9,0x4b534ac3,0x40934238,0x3f334429,0xcbfecbf7,0x4bf34bba,0x39013dd5,0x4bfd4c00,0xc1bdb89d,0xbb5cb1e4,0xcbdfcbff,
0x4be94bf5,0xc73ac51a,0xc0c5be9d,0xcb23cb95,0x4bc54bd9,0xc97ec89a,0xc3a8c238,0xc9d1ca8b,0x4b8f4bac,0xcaecca46,0xc53dc48a,0xc803c8f7,
0xcba3cbfc,0x469b3d71,0x44c63bc0,0x4b494bf9,0xc9a5cad7,0x4b27498c,0x49ab4826,0x472949c4,0xc4b4c81e,0x4bd04bf0,0x4ba64adc,0xc2e43fe2,
0x41eebb2a,0x48fc4aca,0x4bdd4bfd,0xca42c83c,0x4ad44bf4,0xc8fac048,0xc82cbf01,0xca44cbee,0x409f4869,0xcbe1cb7b,0xcbebcaad,0x418bc5ae,
0xc95ac4a2,0xc514ca10,0xc9f3cba8,0x4b964939,0xcbfecb5f,0x497542cc,0x3901c63a,0x49d94bd1,0xc99ccbe6,0x4a5941d5,0x49b4410f,0x48de4bde,
0x4793c086,0x49814bfa,0x4b0c4beb,0xc9cfbd0d,0x4bda4b3b,0xc934367b,0xc21f46da,0xca14cbff,0x3ee8496a,0xca96cbef,0xcbf4c9e4,0x488bc023,
0x480e4bd4,0xcb57c35f,0xcae5c29b,0xc65ccbc9,0xcb3dc4ba,0xbfb0caf0,0xc6cfcba5,0x4bf147f6,0xc573cb65,0x4be349ca,0x4b86461d,0xc15a4985,
0x4bbe4772,0xc70d474b,0x440b4b15,0xcb2ecb1f,0xc484cbbd,0x4be54472,0x4bad4411,0x41344baf,0x4bd84967,0xc7eb4892,0xc25149e6,0xcaf4ca91,
0xc90d4567,0xc5d1cbfb,0xca34cb88,0x4b743ca9,0xc645cbec,0x4b9f497a,0x4b5c407a,0xc4de49d5,0x39344ba1,0xcbf9c531,0xcbfec4d2,0x3d3fcb91,
0xc95ccb68,0x4b52c14d,0x49f1c60b,0x46734be4,0x4beb4788,0xc8e648ed,0xc0934b0f,0xca53ca4e,0xcad24276,0x4128cb56,0xc82ecbd6,0x4be54662,
0x4282cb80,0x4b9345ee,0x4bd54590,0xc5264b6e,0x3e204bfd,0xcbcdc45a,0xcbf7baf8,0x4315cbb3,0xc62ecbc2,0x4bf24172,0x4b61c3cd,0xbf974be2,
0x49234ad5,0xcc00bc44,0xca224829,0x3376cbfb,0xc6f64b5b,0xcab9c6a7,0xcb34c64b,0x4856cb47,0x4821cb09,0x49364942,0x4ada479e,0xca124a08,
0xc8be4aa8,0xc68acac1,0xca72c871,0x4b4dc849,0x4950ca38,0x403c4bb2,0x49fb4908,0xcbee4460,0x4921cb31,0x4978475c,0x4a244702,0xc9d74b1b,
0xcb6648bb,0xbc90cb55,0xc617ca73,0x4bfbc668,0x4bf7c0b8,0xc8954bb6,0xbe074bea,0xca8fc441,0xcab2c549,0x4bb0c8a7,0x4861cb8d,0x446c4a82,
0xca774b03,0xc7c5c806,0xc8b6c7b4,0x4afecaea,0x4bc1c213,0xc84c4bff,0xc3d94bdb,0xcac0b7a8,0xc6e5c912,0x4bfbc734,0x4b38ca30,0xbc774b25,
0xc6b24c00,0xc6a1c890,0xcb442f12,0x4b48ca93,0x4b6bcad0,0x4423485c,0x45ff4831,0xcbba4ab6,0xc910c3f1,0x4b78cb20,0x4a32cbc0,0x45b94745,
0xc86b4bfd,0xc740c5bf,0xcaab3a61,0x4b22cb77,0x4baec57e,0xcab74bba,0xc47e4b83,0xc859c429,0xcbec4a9a,0xb420c8ae,0xc06ec885,0x4c00ca7d,
0x39fd491c,0xcbb548e3,0xcbfe4a28,0x444eca55,0x4bfec9a9,0xc8414b76,0xb9ca49a7,0xcac645c5,0x4061ca26,0x4949bd26,0x4bedc91e,0xca014bf9,
0x4bf4ca5f,0xc34648fe,0xbecf48d7,0xcbca4a40,0x4876cb40,0x48e8c2d8,0x4aa4c6c3,0xca514bd1,0xc799ba2f,0x4c00cb26,0x4b0acbfe,0xb54d472f,
0xcc004ae4,0x492acb4b,0xb11bc811,0x4a1cc696,0xcb824a20,0x4750c94b,0x4584c925,0x4b1dc9ff,0xcb8a4c00,0xb5b2c32e,0xc55bad7f,0x4bffcbcc,
0xc8164a2e,0xc7f14447,0xcae14914,0x4af2cbb5,0x41034207,0xcacd498e,0xcbe74bdb,0x4836c9c1,0x4a9dc9de,0xc9474995,0xc8804971,0xca0349bb,
0x4ba6cb37,0xc89f48f5,0xc4ae46eb,0xca884a48,0x4c00cbea,0xc7d54846,0x2bdb40ac,0xcafa4ac3,0x4ba2cbe8,0xc6564718,0x44ccc0ea,0xcb584b2c,
0xc9534997,0x4a94c9db,0x49f9c9b9,0x488dc973,0xc8c0490b,0x4b9acb2a,0x4a70ca36,0x44fcc71e,0xc8244873,0x4bffcbe2,0x4ad9caa6,0x3744c17f,
0xc6fc47a4,0x4bbbcbf2,0x4b33cb07,0xc41d3f65,0x476cc94e,0xcb7d4a1e,0xcb1649fd,0xc5a24928,0xa8b6c39c,0xcb974c00,0xcc004bc5,0x450e34e9,
0xc77d43c0,0xc84e4a4f,0xcb124bc3,0x4abec8eb,0xca9b4955,0x3f33433a,0xc88349f7,0x4bf3cbcb,0xc3834901,0x4bf3ca5d,0x4bc7ca3e,0x3f4cc8d9,
0x48c8c269,0x4897cb4c,0x4a6acbd6,0xca8d4690,0x4bfdcb0d,0xc724bcc2,0x3ac5c78e,0xcb294bfa,0x496ecb69,0xcbff4abb,0xc9e04605,0xb86b4854,
0xb052c8b1,0xcbee4a98,0xcc004a7b,0x402f4888,0xcba948cd,0x36df4931,0xc49c4a66,0x4bffca16,0xc8784b89,0x4bfac983,0x4aa2c561,0x3cf4c9cc,
0x4903b966,0x41c9ca57,0x4a3ccbfe,0xcbde48e1,0x4405485e,0x4b70cacf,0x4bbecab4,0xc5e2c834,0x4b87cb13,0xc8f0c42f,0xc56dc777,0xca4c4bb9,
0xc6c9c622,0xc8a24bff,0xcb3f4b64,0x4a86b616,0xcae74ba4,0x4b92c4ea,0x480b44c0,0x452ccb9d,0xc7a9c809,0xca804b01,0xcb064ae9,0x48a947ba,
0xc86e4bfe,0x4bb7c1a4,0x4aa93998,0x443bcbe0,0x4bf5c6d4,0xc66dc93b,0x3e84cb3c,0xcb534a0e,0xc5fac8cf,0xc7564bff,0xcb6c4a65,0x4b1c3806,
0x496c4761,0x492dcb30,0x49e2cb19,0xca1ac707,0xba93cb60,0xcb7548a4,0xcbfd4634,0x45cb4a84,0xc8ca4ba7,0x4bf0bfc9,0x4a6844a8,0x400acbf1,
0x4bc7c866,0xca7fc5dc,0xc377caaf,0xc8ac4b72,0xcab0c6ad,0xc7134b5a,0xc8634b45,0x4b2d4651,0x49174957,0x4844cafb,0x4a2cc9f5,0xcac5c7d0,
0xc611cadd,0xc8f24a8a,0xcb67481c,0x4a4a489d,0x3da34bc6,0x4993ca05,0x4bf8c390,0xc9bdc944,0x4b8e45f4,0x42bfcb7f,0x4543cb6d,0xcbd2c596,
0xcbc4c490,0x3cdb4bfb,0xc3b44bab,0x4bfa3c5e,0x4be94244,0xc5b3cbcf,0x40d1cbd8,0xcb7a42fd,0xcbfcbeb6,0x48dc4afd,0xbb8e4bf5,0x4a5bc7ca,
0xcbf8c537,0x38394ba0,0xbdbc4b90,0x4bff44d8,0x4b62c0de,0xc93dcb73,0xc628cbe8,0xca0c45d7,0xc91948c3,0x4be047e6,0x4a2a4a6e,0x4197caf5,
0x428ecb35,0xcb004141,0xcbd5c6f1,0x47bf4be4,0x4be74478,0xc466cbbc,0xc0f6cbaf,0xcbb1c417,0xc819487b,0x4bcf497c,0x4adf4aa1,0x42f0c9d3,
0xc555cbf6,0xc9404502,0xcb8bbe52,0x4a0a4b99,0x4b8149b2,0xc59ccbdf,0x458ac99e,0xcb7ec1b0,0xcb5dc36b,0x48004bd3,0x463f4bc8,0x4aed42a7,
0xbe6bcae2,0xcb4ec4f0,0xcbf6c813,0x46844b9c,0x4bd749ef,0xc4f6cb50,0x425dc95e,0xcb9bc67f,0xc7af46be,0x4bd347fb,0x4b044b41,0xc2b3caef,
0x4a6341e2,0xc991cbe6,0xc8d2cbdd,0xc9bfc11c,0x49634bf7,0x47dbc016,0x49ea3dee,0xcaf8cbef,0xc965a248,0x4bcd4b51,0x49e84c00,0x4322c679,
0xca61cbf7,0x3c12492f,0xc8d43dd5,0x4bfc4a18,0xc906c055,0x4acb4bf3,0x4a3a4bed,0x48393f1a,0xcbdacb85,0x3ffb4851,0xc22c4579,0x4bf04abc,
0xc496c9ec,0xc98ac508,0xcbaac961,0x49c64b98,0x49b743fd,0xcbf9cb7c,0xc99acbbf,0xbd5845a8,0x46b83d8a,0xcb9ecbfc,0xcb43cbf8,0xc4e4bbf2,
0x4b3949a0,0xc988cac8,0xc6e0c9b0,0xc9c8c83e,0x4bc14bf6,0xc435c7e0,0x43e5be39,0xcbb8caf7,0x48b44a9f,0x4352b484,0x4a79487e,0xcbcacc00,
0xc1fab8cf,0x4bfc4c00,0x4bdc4bff,0x3c2b32ad,0xc783c54f,0x4be34bf2,0x4b104b8c,0x41663f7e,0xc9aec8c5,0x4bb44bce,0x49a34a6c,0x44544309,
0xcb18ca75,0x4b6f4b94,0x476748b9,0x45e84520,0x4bfd4c00,0x41bd389d,0xbb5cb1e4,0x4bdf4bff,0x4be94bf5,0x473a451a,0xc0c5be9d,0x4b234b95,
0x4bc54bd9,0x497e489a,0xc3a8c238,0x49d14a8b,0x4b8f4bac,0x4aec4a46,0xc53dc48a,0x480348f7,0xcba3cbfc,0xc69bbd71,0x44c63bc0,0xcb49cbf9,
0xc9a5cad7,0xcb27c98c,0x49ab4826,0xc729c9c4,0xc4b4c81e,0xcbd0cbf0,0x4ba64adc,0x42e4bfe2,0x41eebb2a,0xc8fccaca,0x4bdd4bfd,0x4a42483c,
0x4ad44bf4,0x48fa4048,0xc82cbf01,0x4a444bee,0x409f4869,0x4be14b7b,0xcbebcaad,0xc18b45ae,0xc95ac4a2,0x45144a10,0xc9f3cba8,0xcb96c939,
0xcbfecb5f,0xc975c2cc,0x3901c63a,0xc9d9cbd1,0xc99ccbe6,0xca59c1d5,0x49b4410f,0xc8decbde,0x4793c086,0xc981cbfa,0x4b0c4beb,0x49cf3d0d,
0x4bda4b3b,0x4934b67b,0xc21f46da,0x4a144bff,0x3ee8496a,0x4a964bef,0xcbf4c9e4,0xc88b4023,0x480e4bd4,0x4b57435f,0xcae5c29b,0x465c4bc9,
0xcb3dc4ba,0x3fb04af0,0xc6cfcba5,0xcbf1c7f6,0xc573cb65,0xcbe3c9ca,0x4b86461d,0x415ac985,0x4bbe4772,0x470dc74b,0x440b4b15,0x4b2e4b1f,
0xc484cbbd,0xcbe5c472,0x4bad4411,0xc134cbaf,0x4bd84967,0x47ebc892,0xc25149e6,0x4af44a91,0xc90d4567,0x45d14bfb,0xca34cb88,0xcb74bca9,
0xc645cbec,0xcb9fc97a,0x4b5c407a,0x44dec9d5,0x39344ba1,0x4bf94531,0xcbfec4d2,0xbd3f4b91,0xc95ccb68,0xcb52414d,0x49f1c60b,0xc673cbe4,
0x4beb4788,0x48e6c8ed,0xc0934b0f,0x4a534a4e,0xcad24276,0xc1284b56,0xc82ecbd6,0xcbe5c662,0x4282cb80,0xcb93c5ee,0x4bd54590,0x4526cb6e,
0x3e204bfd,0x4bcd445a,0xcbf7baf8,0xc3154bb3,0xc62ecbc2,0xcbf2c172,0x4b61c3cd,0x3f97cbe2,0x49234ad5,0x4c003c44,0xca224829,0xb3764bfb,
0xc6f64b5b,0x4ab946a7,0xcb34c64b,0xc8564b47,0x4821cb09,0xc936c942,0x4ada479e,0x4a12ca08,0xc8be4aa8,0x468a4ac1,0xca72c871,0xcb4d4849,
0x4950ca38,0xc03ccbb2,0x49fb4908,0x4beec460,0x4921cb31,0xc978c75c,0x4a244702,0x49d7cb1b,0xcb6648bb,0x3c904b55,0xc617ca73,0xcbfb4668,
0x4bf7c0b8,0x4895cbb6,0xbe074bea,0x4a8f4441,0xcab2c549,0xcbb048a7,0x4861cb8d,0xc46cca82,0xca774b03,0x47c54806,0xc8b6c7b4,0xcafe4aea,
0x4bc1c213,0x484ccbff,0xc3d94bdb,0x4ac037a8,0xc6e5c912,0xcbfb4734,0x4b38ca30,0x3c77cb25,0xc6b24c00,0x46a14890,0xcb442f12,0xcb484a93,
0x4b6bcad0,0xc423c85c,0x45ff4831,0x4bbacab6,0xc910c3f1,0xcb784b20,0x4a32cbc0,0xc5b9c745,0xc86b4bfd,0x474045bf,0xcaab3a61,0xcb224b77,
0x4baec57e,0x4ab7cbba,0xc47e4b83,0x48594429,0xcbec4a9a,0x342048ae,0xc06ec885,0xcc004a7d,0x39fd491c,0x4bb5c8e3,0xcbfe4a28,0xc44e4a55,
0x4bfec9a9,0x4841cb76,0xb9ca49a7,0x4ac6c5c5,0x4061ca26,0xc9493d26,0x4bedc91e,0x4a01cbf9,0x4bf4ca5f,0x4346c8fe,0xbecf48d7,0x4bcaca40,
0x4876cb40,0xc8e842d8,0x4aa4c6c3,0x4a51cbd1,0xc799ba2f,0xcc004b26,0x4b0acbfe,0x354dc72f,0xcc004ae4,0xc92a4b4b,0xb11bc811,0xca1c4696,
0xcb824a20,0xc750494b,0x4584c925,0xcb1d49ff,0xcb8a4c00,0x35b2432e,0xc55bad7f,0xcbff4bcc,0xc8164a2e,0x47f1c447,0xcae14914,0xcaf24bb5,
0x41034207,0x4acdc98e,0xcbe74bdb,0xc83649c1,0x4a9dc9de,0x4947c995,0xc8804971,0x4a03c9bb,0x4ba6cb37,0x489fc8f5,0xc4ae46eb,0x4a88ca48,
0x4c00cbea,0x47d5c846,0x2bdb40ac,0x4afacac3,0x4ba2cbe8,0x4656c718,0x44ccc0ea,0x4b58cb2c,0xc9534997,0xca9449db,0x49f9c9b9,0xc88d4973,
0xc8c0490b,0xcb9a4b2a,0x4a70ca36,0xc4fc471e,0xc8244873,0xcbff4be2,0x4ad9caa6,0xb744417f,0xc6fc47a4,0xcbbb4bf2,0x4b33cb07,0x441dbf65,
0x476cc94e,0x4b7dca1e,0xcb1649fd,0x45a2c928,0xa8b6c39c,0x4b97cc00,0xcc004bc5,0xc50eb4e9,0xc77d43c0,0x484eca4f,0xcb124bc3,0xcabe48eb,
0xca9b4955,0xbf33c33a,0xc88349f7,0xcbf34bcb,0xc3834901,0xcbf34a5d,0x4bc7ca3e,0xbf4c48d9,0x48c8c269,0xc8974b4c,0x4a6acbd6,0x4a8dc690,
0x4bfdcb0d,0x47243cc2,0x3ac5c78e,0x4b29cbfa,0x496ecb69,0x4bffcabb,0xc9e04605,0x386bc854,0xb052c8b1,0x4beeca98,0xcc004a7b,0xc02fc888,
0xcba948cd,0xb6dfc931,0xc49c4a66,0xcbff4a16,0xc8784b89,0xcbfa4983,0x4aa2c561,0xbcf449cc,0x4903b966,0xc1c94a57,0x4a3ccbfe,0x4bdec8e1,
0x4405485e,0xcb704acf,0x4bbecab4,0x45e24834,0x4b87cb13,0x48f0442f,0xc56dc777,0x4a4ccbb9,0xc6c9c622,0x48a2cbff,0xcb3f4b64,0xca863616,
0xcae74ba4,0xcb9244ea,0x480b44c0,0xc52c4b9d,0xc7a9c809,0x4a80cb01,0xcb064ae9,0xc8a9c7ba,0xc86e4bfe,0xcbb741a4,0x4aa93998,0xc43b4be0,
0x4bf5c6d4,0x466d493b,0x3e84cb3c,0x4b53ca0e,0xc5fac8cf,0x4756cbff,0xcb6c4a65,0xcb1cb806,0x496c4761,0xc92d4b30,0x49e2cb19,0x4a1a4707,
0xba93cb60,0x4b75c8a4,0xcbfd4634,0xc5cbca84,0xc8ca4ba7,0xcbf03fc9,0x4a6844a8,0xc00a4bf1,0x4bc7c866,0x4a7f45dc,0xc377caaf,0x48accb72,
0xcab0c6ad,0x4713cb5a,0xc8634b45,0xcb2dc651,0x49174957,0xc8444afb,0x4a2cc9f5,0x4ac547d0,0xc611cadd,0x48f2ca8a,0xcb67481c,0xca4ac89d,
0x3da34bc6,0xc9934a05,0x4bf8c390,0x49bd4944,0x4b8e45f4,0xc2bf4b7f,0x4543cb6d,0x4bd24596,0xcbc4c490,0xbcdbcbfb,0xc3b44bab,0xcbfabc5e,
0x4be94244,0x45b34bcf,0x40d1cbd8,0x4b7ac2fd,0xcbfcbeb6,0xc8dccafd,0xbb8e4bf5,0xca5b47ca,0xcbf8c537,0xb839cba0,0xbdbc4b90,0xcbffc4d8,
0x4b62c0de,0x493d4b73,0xc628cbe8,0x4a0cc5d7,0xc91948c3,0xcbe0c7e6,0x4a2a4a6e,0xc1974af5,0x428ecb35,0x4b00c141,0xcbd5c6f1,0xc7bfcbe4,
0x4be74478,0x44664bbc,0xc0f6cbaf,0x4bb14417,0xc819487b,0xcbcfc97c,0x4adf4aa1,0xc2f049d3,0xc555cbf6,0x4940c502,0xcb8bbe52,0xca0acb99,
0x4b8149b2,0x459c4bdf,0x458ac99e,0x4b7e41b0,0xcb5dc36b,0xc800cbd3,0x463f4bc8,0xcaedc2a7,0xbe6bcae2,0x4b4e44f0,0xcbf6c813,0xc684cb9c,
0x4bd749ef,0x44f64b50,0x425dc95e,0x4b9b467f,0xc7af46be,0xcbd3c7fb,0x4b044b41,0x42b34aef,0x4a6341e2,0x49914be6,0xc8d2cbdd,0x49bf411c,
0x49634bf7,0xc7db4016,0x49ea3dee,0x4af84bef,0xc965a248,0xcbcdcb51,0x49e84c00,0xc3224679,0xca61cbf7,0xbc12c92f,0xc8d43dd5,0xcbfcca18,
0xc906c055,0xcacbcbf3,0x4a3a4bed,0xc839bf1a,0xcbdacb85,0xbffbc851,0xc22c4579,0xcbf0cabc,0xc496c9ec,0x498a4508,0xcbaac961,0xc9c6cb98,
0x49b743fd,0x4bf94b7c,0xc99acbbf,0x3d58c5a8,0x46b83d8a,0x4b9e4bfc,0xcb43cbf8,0x44e43bf2,0x4b3949a0,0x49884ac8,0xc6e0c9b0,0x49c8483e,
0x4bc14bf6,0x443547e0,0x43e5be39,0x4bb84af7,0x48b44a9f,0xc3523484,0x4a79487e,0x4bca4c00,0xc1fab8cf,0xcbfccc00,0x4bdc4bff,0xbc2bb2ad,
0xc783c54f,0xcbe3cbf2,0x4b104b8c,0xc166bf7e,0xc9aec8c5,0xcbb4cbce,0x49a34a6c,0xc454c309,0xcb18ca75,0xcb6fcb94,0x476748b9,0xc5e8c520,
0x4b494b6e,0xcbc7cb6d,0xc69bc5ee,0xc383c5f4,0x4af44b20,0xcbfdcbf7,0xc7ebc745,0x3a93bdee,0x4a8f4ac3,0xcb8bcbd9,0xc895c846,0x45554238,
0x4a1c4a57,0xca79cb15,0xc92ac8e1,0x48b44772,0x48fa46a7,0xb0524537,0x4a444b47,0xcc00cb90,0x4b524a55,0xc917c579,0x467348e3,0xca2ccb85,
0x4bfb4be2,0xcbd7cadc,0xbc77417f,0xc25dc81e,0x4acd4b9d,0xcb18cbec,0xc836c4ea,0x4767407a,0xc8decb1b,0x4bbe4baf,0x4a59475c,0xc4054478,
0x4315c2d8,0x43b449a0,0x4bcd4bd1,0xcbc4c9b0,0x4b2248eb,0xc9e8c4a2,0x47404a4f,0xc965cba8,0x4b584bff,0xcb8fcbd6,0xc6563806,0x453dc276,
0xcb57c806,0x47a9c36b,0xc65ccaea,0x4b064bc8,0xc936cbcc,0x4b624b8c,0x4a12432e,0xc628454f,0x4841bcc2,0xc49646da,0x4ac64bfa,0xcbaacb3b,
0x4bbb4b72,0xcbddcad5,0xc41d45dc,0x41eec829,0x41344ab6,0xc9e2cbdd,0xcbe5c85c,0x496cc1e2,0xcbfbc8f5,0x4adf3e9d,0xbc90ca48,0x48194bf5,
0x354dc9cc,0x43e54b65,0x4c004983,0xcbc1c61d,0x4bf34a05,0xcbfec908,0xbf334944,0x3901ca38,0x4bf948ae,0xcab04055,0xbd3f4a7d,0xc863cbed,
0xc84c471e,0x3e6bcad7,0xcac0cb2a,0x4bf64826,0xc7f1cbff,0x49ae4b88,0x4af23616,0xc9a34567,0x4bff47ca,0xcbf4c549,0x386b4afd,0xbee8cb8d,
0x4526ca40,0x45434bf8,0x4b9348fe,0xcb8e3d8a,0x45b94c00,0xc9eacaad,0xcb7834e9,0x4963c869,0xcafaca0e,0x4bc54788,0x47d5c93b,0xc3a84b0f,
0x4bde4141,0xcbbe2f12,0x41c94be4,0xc40bcc00,0xcab9c94b,0x4bf8b8cf,0x4856c9ff,0x3dbc4bff,0x4bb54690,0xcbda4086,0xc44e4b4c,0xc22ccbeb,
0xcbffbfc9,0x4ba6c3cd,0xb744cbf1,0x44b44bc2,0x4b92c1b0,0xcb5c457e,0x452c4bdf,0xc645cb83,0xc9d749bb,0x40f6cc00,0xc978c995,0x4be731e4,
0x4a51c931,0xc6e04ba5,0x48e84a16,0xcb39c4ba,0xcabe489d,0x495acaa8,0xc84eca8a,0x49f34871,0x4b1cc7fb,0xcad2491e,0x47564aef,0xc82eca26,
0x47c549db,0xcb5dbbc0,0xcafe4973,0x463fcbfc,0xb5b2cbb9,0x47834967,0x4bffc42f,0xcb1049e6,0xc7244bcf,0x421fcbea,0xcb29c2fd,0x4bdac0b8,
0x4a7fca18,0xca224ae4,0x48ac492f,0xc923c811,0x4bbac928,0xc8d24bf4,0x44234a1e,0xca63bf01,0xca88c1a4,0x4be9c60b,0x489fcbe0,0xc0c54b68,
0x3cf44af5,0xc573c912,0xcbfa47e6,0x4b86ca30,0x49bdcb7c,0xc9504bdb,0x499345a8,0xc9fbc207,0xb420ca5d,0x4906410f,0x4c00c8d9,0xca3a4be6,
0xcb9a4a84,0x49abcbfd,0xc4fcc8a4,0x49a53af8,0x48a24502,0xca343a61,0xca864b99,0x490dcbfd,0x48dccc00,0xc8614be8,0x4a5b3484,0xcab240ea,
0xcbca4888,0x4b43cbd4,0x4346ca98,0x46b8429b,0xc50e4afb,0xc09fc79e,0xcb9747d0,0x4bebcb09,0x4b53c67f,0xcbeb49a9,0xc66d4b50,0x4093c9a7,
0x47bfcb94,0xc6b24b07,0x4b00c520,0xcb4447a4,0xc7504acf,0xc1fac411,0xcb1d4834,0x4bdccbbd,0x4897bc5e,0xcb0c48bb,0xca8d4bfb,0x4793ca73,
0x4bf0cb51,0xcb614bfe,0x400a4679,0xc62eba2f,0x459cca46,0xc47e4955,0x4b7ec8f7,0xcbae49f7,0x4a03c7ba,0xcbfd4ba1,0xc9474b01,0x3b5cc4d2,
0x4bffcb73,0xcb3d4bdb,0xb6df45d7,0xc6cf4213,0x4a4acb98,0xc8be4a2e,0x48f2c508,0xca724914,0x42b3c83c,0xc0614605,0x4bd3caca,0xcbed4b69,
0x4a94cb30,0xc4c64590,0x488dc707,0xcba34b80,0x48f0c9d3,0xc25143f1,0x4a4cc97c,0xcbd84bc0,0x45b3c7e0,0xbe0740ac,0x4b7acaf7,0xcbf74bea,
0x3c12c2cc,0x311b3966,0x4bfccbd1,0xcc004bfe,0xc5a24651,0x4ad4cb5b,0x4b7dcb5a,0xc82c464b,0xc43b44f0,0x495cca28,0x4bb7cb9c,0xc9f1491c,
0xc1974309,0x46e5c873,0x4be0cbce,0xcb384aa6,0xbd584023,0x4103c4c0,0x4bf9cbef,0xcbe74ba4,0xcbf34b7f,0x49b4c702,0xbf4c4596,0x499ccb31,
0xcb754bef,0x4bf7cb40,0x45cbc016,0x3e20c6c3,0xc9404a8b,0x4aabcbc3,0x4a0ac89a,0xc86b43c0,0xc352474b,0x44ccc8cf,0x4bcacb1f,0xcba24a65,
0xc02fc4d8,0xc80e4b03,0xcbee4ba0,0x4ae5c7b4,0xcac54851,0x4821ad7f,0xc8444abc,0x4adacc00,0xcb9b4bf0,0x4bfecb0d,0x44f63fe2,0xb9cac78e,
0xc5e849d5,0x46fccaaf,0x4b6fc97a,0xcb334866,0x4b70cbbc,0xcbad4831,0xc5e2c417,0xc4844ad0,0xbcdbc83e,0xc6174b37,0xcbfa4ac8,0x4b66c6eb,
0xcbcd4939,0x4b0ac561,0xc3224a10,0x4799cb89,0xc8034b56,0x4883cbc6,0x4aecc662,0xca9b4390,0x48a942a7,0x3934ca9a,0x4a80cbd3,0xcbfe4885,
0x4a0ccbf2,0xcbc14a36,0xc93dbf7e,0x43d9490b,0xc9c6b67b,0x48164622,0xc98a4bff,0x4ae1cb64,0xc8fc4bfb,0x496ecbf5,0x4a42bc44,0xc9e0beb6,
0xc92d4be6,0x4bd5c8d7,0x4a1a411c,0xc282ca5f,0x4bcfc51a,0xca32c39c,0x42f0cb95,0xc9104bc5,0xc435c985,0xabdb4b3c,0xcbb849ca,0x4c00c6d4,
0xc9d94bb2,0x4a3ccb35,0x49754460,0xc903c6f1,0xcb2dbf1a,0x46f64a20,0xc7134bf3,0x4b34c925,0x468449c4,0x39fdcbd6,0x4b4ec98c,0xcbfe4269,
0x4454cbfb,0xc8244ba7,0xcbb43ca9,0x4ad944a8,0xca964a82,0x4ae7c99e,0x488b48a7,0xc80bc9b2,0x42bfcbfc,0xca244971,0xcbd2bbf2,0x492149de,
0xc7db4b7b,0x4aa4c8cd,0x4af845ae,0xc876ca66,0x49d1ca4e,0xcb12481c,0xc97ec8ed,0x477d4add,0xcb2e4890,0x4b6cc6be,0x470d4a93,0xc5facb41,
0x4bff32ad,0xca77c997,0xb839cc00,0xc8b649b9,0xcbf03d0d,0x4b8a4777,0x3ffb4bfa,0x455bcb13,0x4bd0c172,0xcbfdc244,0xc2e4cbe2,0xbac54bd8,
0xcb9f4429,0x4bc7bdd5,0x44de4bba,0xc377cbf7,0x44664bff,0x45ffc9fd,0x4bb1b89d,0xcb6bc94e,0xc988caf0,0x44ae4bfe,0xc9c847f6,0x4ba63998,
0x4b964849,0xcaa2ca6e,0x4514cac1,0xc87848c3,0xcbe5bd26,0x4bf843fd,0x41284bf9,0xbda3cbbf,0xcaed3d71,0x4bec4901,0x48004bf9,0x406eca3e,
0x4166ca91,0xc8c04634,0xcbe3c892,0x4a704b60,0x49344bb6,0xc6c9cbf6,0x4a14c441,0xcb3fbe52,0xcc00c696,0x4bfc487e,0x33764b4b,0x3b8eca9f,
0xc991cbee,0x3ecf4a7b,0xc9bf4048,0x4bf448b1,0x4b23414d,0xcc00c957,0xc73acbe4,0x28b649f5,0x415a4b25,0x3e84c95e,0x4be34734,0xcbf5c9ef,
0xcbeec98e,0x4bd54a75,0xc03c49c1,0x428ec8b9,0x4839c1d5,0xcb82c85e,0xcacbcbde,0x45844ab4,0x4b274bb3,0xc8c8cbab,0x4729c45a,0xca6ac490,
0xc5d145bf,0x48ca2248,0x4b744b77,0xca68cc00,0xcbb0cb2c,0x4b814bac,0xc46c4718,0x458ac48a,0x4b9e4bc9,0xc880cae9,0x44e4c35f,0xca9dc809,
0x418b4942,0x449cc0de,0x4be14a08,0xcba9cbe8,0xca53c5c5,0x4b674961,0x48e64b76,0xc611c9ec,0xcb48cbf2,0x4b044bfd,0xc6a13f65,0x47af3b2a,
0xbc2b4472,0x49534761,0x4bfc4baf,0xc9f9cb19,0xc981c668,0x4b874aa1,0x49cf4b55,0xc56dc87b,0xcbf2cb26,0x4be94bf6,0x3f97472f,0x40d1be39,
0xcab7cbcb,0x4a614b5f,0xc859c33a,0x48d4463a,0xcbdfcb91,0x4b164b45,0x41bd4531,0x476c46ad,0xcbf1cbff,0x4aa94ae2,0xbfb037a8,0x486e4813,
0xcb4dcbb5,0x4a2a4a6c,0xc68ac447,0x491948c5,0xca01cabb,0x499a49e4,0xc949c854,0x49b7496a,0x4b494b6e,0x4bc74b6d,0xc69bc5ee,0x438345f4,
0x4af44b20,0x4bfd4bf7,0xc7ebc745,0xba933dee,0x4a8f4ac3,0x4b8b4bd9,0xc895c846,0xc555c238,0x4a1c4a57,0x4a794b15,0xc92ac8e1,0xc8b4c772,
0x48fa46a7,0x3052c537,0x4a444b47,0x4c004b90,0x4b524a55,0x49174579,0x467348e3,0x4a2c4b85,0x4bfb4be2,0x4bd74adc,0xbc77417f,0x425d481e,
0x4acd4b9d,0x4b184bec,0xc836c4ea,0xc767c07a,0xc8decb1b,0xcbbecbaf,0x4a59475c,0x4405c478,0x4315c2d8,0xc3b4c9a0,0x4bcd4bd1,0x4bc449b0,
0x4b2248eb,0x49e844a2,0x47404a4f,0x49654ba8,0x4b584bff,0x4b8f4bd6,0xc6563806,0xc53d4276,0xcb57c806,0xc7a9436b,0xc65ccaea,0xcb06cbc8,
0xc936cbcc,0xcb62cb8c,0x4a12432e,0x4628c54f,0x4841bcc2,0x4496c6da,0x4ac64bfa,0x4baa4b3b,0x4bbb4b72,0x4bdd4ad5,0xc41d45dc,0xc1ee4829,
0x41344ab6,0x49e24bdd,0xcbe5c85c,0xc96c41e2,0xcbfbc8f5,0xcadfbe9d,0xbc90ca48,0xc819cbf5,0x354dc9cc,0xc3e5cb65,0x4c004983,0x4bc1461d,
0x4bf34a05,0x4bfe4908,0xbf334944,0xb9014a38,0x4bf948ae,0x4ab0c055,0xbd3f4a7d,0x48634bed,0xc84c471e,0xbe6b4ad7,0xcac0cb2a,0xcbf6c826,
0xc7f1cbff,0xc9aecb88,0x4af23616,0x49a3c567,0x4bff47ca,0x4bf44549,0x386b4afd,0x3ee84b8d,0x4526ca40,0xc543cbf8,0x4b9348fe,0x4b8ebd8a,
0x45b94c00,0x49ea4aad,0xcb7834e9,0xc9634869,0xcafaca0e,0xcbc5c788,0x47d5c93b,0x43a8cb0f,0x4bde4141,0x4bbeaf12,0x41c94be4,0x440b4c00,
0xcab9c94b,0xcbf838cf,0x4856c9ff,0xbdbccbff,0x4bb54690,0x4bdac086,0xc44e4b4c,0x422c4beb,0xcbffbfc9,0xcba643cd,0xb744cbf1,0xc4b4cbc2,
0x4b92c1b0,0x4b5cc57e,0x452c4bdf,0x46454b83,0xc9d749bb,0xc0f64c00,0xc978c995,0xcbe7b1e4,0x4a51c931,0x46e0cba5,0x48e84a16,0x4b3944ba,
0xcabe489d,0xc95a4aa8,0xc84eca8a,0xc9f3c871,0x4b1cc7fb,0x4ad2c91e,0x47564aef,0x482e4a26,0x47c549db,0x4b5d3bc0,0xcafe4973,0xc63f4bfc,
0xb5b2cbb9,0xc783c967,0x4bffc42f,0x4b10c9e6,0xc7244bcf,0xc21f4bea,0xcb29c2fd,0xcbda40b8,0x4a7fca18,0x4a22cae4,0x48ac492f,0x49234811,
0x4bbac928,0x48d2cbf4,0x44234a1e,0x4a633f01,0xca88c1a4,0xcbe9460b,0x489fcbe0,0x40c5cb68,0x3cf44af5,0x45734912,0xcbfa47e6,0xcb864a30,
0x49bdcb7c,0x4950cbdb,0x499345a8,0x49fb4207,0xb420ca5d,0xc906c10f,0x4c00c8d9,0x4a3acbe6,0xcb9a4a84,0xc9ab4bfd,0xc4fcc8a4,0xc9a5baf8,
0x48a24502,0x4a34ba61,0xca864b99,0xc90d4bfd,0x48dccc00,0x4861cbe8,0x4a5b3484,0x4ab2c0ea,0xcbca4888,0xcb434bd4,0x4346ca98,0xc6b8c29b,
0xc50e4afb,0x409f479e,0xcb9747d0,0xcbeb4b09,0x4b53c67f,0x4bebc9a9,0xc66d4b50,0xc09349a7,0x47bfcb94,0x46b2cb07,0x4b00c520,0x4b44c7a4,
0xc7504acf,0x41fa4411,0xcb1d4834,0xcbdc4bbd,0x4897bc5e,0x4b0cc8bb,0xca8d4bfb,0xc7934a73,0x4bf0cb51,0x4b61cbfe,0x400a4679,0x462e3a2f,
0x459cca46,0x447ec955,0x4b7ec8f7,0x4baec9f7,0x4a03c7ba,0x4bfdcba1,0xc9474b01,0xbb5c44d2,0x4bffcb73,0x4b3dcbdb,0xb6df45d7,0x46cfc213,
0x4a4acb98,0x48beca2e,0x48f2c508,0x4a72c914,0x42b3c83c,0x4061c605,0x4bd3caca,0x4bedcb69,0x4a94cb30,0x44c6c590,0x488dc707,0x4ba3cb80,
0x48f0c9d3,0x4251c3f1,0x4a4cc97c,0x4bd8cbc0,0x45b3c7e0,0x3e07c0ac,0x4b7acaf7,0x4bf7cbea,0x3c12c2cc,0xb11bb966,0x4bfccbd1,0x4c00cbfe,
0xc5a24651,0xcad44b5b,0x4b7dcb5a,0x482cc64b,0xc43b44f0,0xc95c4a28,0x4bb7cb9c,0x49f1c91c,0xc1974309,0xc6e54873,0x4be0cbce,0x4b38caa6,
0xbd584023,0xc10344c0,0x4bf9cbef,0x4be7cba4,0xcbf34b7f,0xc9b44702,0xbf4c4596,0xc99c4b31,0xcb754bef,0xcbf74b40,0x45cbc016,0xbe2046c3,
0xc9404a8b,0xcaab4bc3,0x4a0ac89a,0x486bc3c0,0xc352474b,0xc4cc48cf,0x4bcacb1f,0x4ba2ca65,0xc02fc4d8,0x480ecb03,0xcbee4ba0,0xcae547b4,
0xcac54851,0xc8212d7f,0xc8444abc,0xcada4c00,0xcb9b4bf0,0xcbfe4b0d,0x44f63fe2,0x39ca478e,0xc5e849d5,0xc6fc4aaf,0x4b6fc97a,0x4b33c866,
0x4b70cbbc,0x4badc831,0xc5e2c417,0x4484cad0,0xbcdbc83e,0x4617cb37,0xcbfa4ac8,0xcb6646eb,0xcbcd4939,0xcb0a4561,0xc3224a10,0xc7994b89,
0xc8034b56,0xc8834bc6,0x4aecc662,0x4a9bc390,0x48a942a7,0xb9344a9a,0x4a80cbd3,0x4bfec885,0x4a0ccbf2,0x4bc1ca36,0xc93dbf7e,0xc3d9c90b,
0xc9c6b67b,0xc816c622,0xc98a4bff,0xcae14b64,0xc8fc4bfb,0xc96e4bf5,0x4a42bc44,0x49e03eb6,0xc92d4be6,0xcbd548d7,0x4a1a411c,0x42824a5f,
0x4bcfc51a,0x4a32439c,0x42f0cb95,0x4910cbc5,0xc435c985,0x2bdbcb3c,0xcbb849ca,0xcc0046d4,0xc9d94bb2,0xca3c4b35,0x49754460,0x490346f1,
0xcb2dbf1a,0xc6f6ca20,0xc7134bf3,0xcb344925,0x468449c4,0xb9fd4bd6,0x4b4ec98c,0x4bfec269,0x4454cbfb,0x4824cba7,0xcbb43ca9,0xcad9c4a8,
0xca964a82,0xcae7499e,0x488b48a7,0x480b49b2,0x42bfcbfc,0x4a24c971,0xcbd2bbf2,0xc921c9de,0xc7db4b7b,0xcaa448cd,0x4af845ae,0x48764a66,
0x49d1ca4e,0x4b12c81c,0xc97ec8ed,0xc77dcadd,0xcb2e4890,0xcb6c46be,0x470d4a93,0x45fa4b41,0x4bff32ad,0x4a774997,0xb839cc00,0x48b6c9b9,
0xcbf03d0d,0xcb8ac777,0x3ffb4bfa,0xc55b4b13,0x4bd0c172,0x4bfd4244,0xc2e4cbe2,0x3ac5cbd8,0xcb9f4429,0xcbc73dd5,0x44de4bba,0x43774bf7,
0x44664bff,0xc5ff49fd,0x4bb1b89d,0x4b6b494e,0xc988caf0,0xc4aecbfe,0xc9c847f6,0xcba6b998,0x4b964849,0x4aa24a6e,0x4514cac1,0x4878c8c3,
0xcbe5bd26,0xcbf8c3fd,0x41284bf9,0x3da34bbf,0xcaed3d71,0xcbecc901,0x48004bf9,0xc06e4a3e,0x4166ca91,0x48c0c634,0xcbe3c892,0xca70cb60,
0x49344bb6,0x46c94bf6,0x4a14c441,0x4b3f3e52,0xcc00c696,0xcbfcc87e,0x33764b4b,0xbb8e4a9f,0xc991cbee,0xbecfca7b,0xc9bf4048,0xcbf4c8b1,
0x4b23414d,0x4c004957,0xc73acbe4,0xa8b6c9f5,0x415a4b25,0xbe84495e,0x4be34734,0x4bf549ef,0xcbeec98e,0xcbd5ca75,0xc03c49c1,0xc28e48b9,
0x4839c1d5,0x4b82485e,0xcacbcbde,0xc584cab4,0x4b274bb3,0x48c84bab,0x4729c45a,0x4a6a4490,0xc5d145bf,0xc8caa248,0x4b744b77,0x4a684c00,
0xcbb0cb2c,0xcb81cbac,0xc46c4718,0xc58a448a,0x4b9e4bc9,0x48804ae9,0x44e4c35f,0x4a9d4809,0x418b4942,0xc49c40de,0x4be14a08,0x4ba94be8,
0xca53c5c5,0xcb67c961,0x48e64b76,0x461149ec,0xcb48cbf2,0xcb04cbfd,0xc6a13f65,0xc7afbb2a,0xbc2b4472,0xc953c761,0x4bfc4baf,0x49f94b19,
0xc981c668,0xcb87caa1,0x49cf4b55,0x456d487b,0xcbf2cb26,0xcbe9cbf6,0x3f97472f,0xc0d13e39,0xcab7cbcb,0xca61cb5f,0xc859c33a,0xc8d4c63a,
0xcbdfcb91,0xcb16cb45,0x41bd4531,0xc76cc6ad,0xcbf1cbff,0xcaa9cae2,0xbfb037a8,0xc86ec813,0xcb4dcbb5,0xca2aca6c,0xc68ac447,0xc919c8c5,
0xca01cabb,0xc99ac9e4,0xc949c854,0xc9b7c96a,0x3cfa3d81,0xbbd0bb9c,0xb3e3b5a1,0x3bc53b8c,0x3c193c83,0xbbffbbf1,0xaa31b0ac,0x3bfe3beb,
0x3abf3b70,0xbbe3bbfb,0x30ac2a31,0x3beb3bfe,0x39853a1c,0xbb7bbbb8,0x35a133e3,0x3b8c3bc5,0x3c703cdd,0xbbf5bbda,0xb35eb53f,0x3bcc3b9a,
0x3b673c0d,0xbbfabc00,0xa9ccb05f,0x3bfe3bed,0x3a293ac2,0xbbbcbbe3,0x305f29cc,0x3bed3bfe,0x3914399a,0xbb3dbb85,0x353f335e,0x3b9a3bcc,
0x3bec3c4f,0xbc00bbfa,0xb2dab4de,0x3bd33ba7,0x3aaf3b47,0xbbdfbbf7,0xa967b012,0x3bfe3bf0,0x399c3a21,0xbb86bbba,0x30122967,0x3bf03bfe,
0x38a9391f,0xbaf5bb44,0x34de32da,0x3ba73bd3,0x3b123ba5,0xbbf0bbfe,0xb257b47e,0x3bd93bb4,0x3a063a88,0xbbb0bbd6,0xa902af8c,0x3bfe3bf2,
0x3919398c,0xbb40bb7e,0x2f8c2902,0x3bf23bfe,0x384238ab,0xbaa2baf7,0x347e3257,0x3bb43bd9,0x3a4c3ac7,0xbbc7bbe4,0xb1d5b420,0x3bdf3bbf,
0x396a39d8,0xbb6dbb9f,0xa89eaef3,0x3bff3bf4,0x389c3900,0xbaecbb31,0x2ef3289e,0x3bf43bff,0x37be383c,0xba46ba9d,0x342031d5,0x3bbf3bdf,
0x399839ff,0xbb83bbae,0xb153b386,0x3be43bca,0x38d73935,0xbb16bb51,0xa839ae5a,0x3bff3bf6,0x3826387d,0xba8abad4,0x2e5a2839,0x3bf63bff,
0x36ff37a3,0xb9e0ba38,0x33863153,0x3bca3be4,0x38f13947,0xbb27bb5b,0xb0d2b2cd,0x3be93bd3,0x384e389e,0xbaadbaed,0xa7a9adc2,0x3bff3bf8,
0x37693800,0xba1aba66,0x2dc227a9,0x3bf83bff,0x364736d6,0xb971b9c8,0x32cd30d2,0x3bd33be9,0x3856389e,0xbab4baed,0xb052b216,0x3bee3bdc,
0x37973810,0xba32ba75,0xa6e0ad2a,0x3bff3bf9,0x36903712,0xb99eb9ea,0x2d2a26e0,0x3bf93bff,0x35943611,0xb8fab94e,0x32163052,0x3bdc3bee,
0x37883800,0xba2aba66,0xafa5b160,0x3bf23be4,0x369f3712,0xb9a7b9ea,0xa617ac93,0x3bff3bfb,0x35bf362e,0xb917b961,0x2c932617,0x3bfb3bff,
0x34e73552,0xb87bb8ca,0x31602fa5,0x3be43bf2,0x367336d6,0xb98cb9c8,0xaea7b0ac,0x3bf53beb,0x35b13611,0xb90db94e,0xa54dabf6,0x3c003bfc,
0x34f43552,0xb885b8ca,0x2bf6254d,0x3bfc3c00,0x343d3498,0xb7ebb83e,0x30ac2ea7,0x3beb3bf5,0x356a35bb,0xb8dcb914,0xada9aff2,0x3bf83bf0,
0x34cb351a,0xb866b8a2,0xa484aac8,0x3c003bfd,0x342f347d,0xb7d5b829,0x2ac82484,0x3bfd3c00,0x332c33c5,0xb6d4b756,0x2ff22da9,0x3bf03bf8,
0x346c34ac,0xb81cb84e,0xacacae8d,0x3bfb3bf5,0x33d9342c,0xb767b7d0,0xa376a999,0x3c003bfe,0x32dd335b,0xb690b6fc,0x29992376,0x3bfe3c00,
0x31e53261,0xb5b3b622,0x2e8d2cac,0x3bf53bfb,0x32ea334d,0xb69bb6f1,0xab5fad2a,0x3bfd3bf9,0x32263288,0xb5eeb645,0xa1e4a86b,0x3c003bff,
0x316331c5,0xb53db596,0x286b21e4,0x3bff3c00,0x30a23103,0xb48ab4e4,0x2d2a2b5f,0x3bf93bfd,0x31093150,0xb4eab52c,0xa967ab91,0x3bfe3bfc,
0x307c30c2,0xb466b4a8,0xa052a67b,0x3c003bff,0x2fde3035,0xb3c0b423,0x267b2052,0x3bff3c00,0x2ec62f52,0xb2b3b33a,0x2b912967,0x3bfc3bfe,
0x2e612eba,0xb251b2a7,0xa6e0a8d0,0x3bff3bff,0x2daf2e08,0xb1a4b1fa,0x9d7fa420,0x3c003c00,0x2cfe2d57,0xb0f6b14d,0x24201d7f,0x3c003c00,
0x2c4d2ca6,0xb048b09f,0x28d026e0,0x3bff3bff,0x297429bf,0xad71adbc,0xa1e4a420,0x3c003c00,0x28dd2928,0xacdbad26,0x98b69f12,0x3c003c00,
0x28462891,0xac44ac90,0x1f1218b6,0x3c003c00,0x275d27f4,0xab5cabf2,0x242021e4,0x3c003c00,0xa344a3a9,0x274427a8,0x1bdb1d7f,0x3c003c00,
0xa27ba2df,0x267b26df,0x124818b6,0x3c003c00,0xa1b2a216,0x25b22616,0x98b69248,0x3c003c00,0xa0e9a14d,0x24e9254d,0x9d7f9bdb,0x3c003c00,
0xac8caccc,0x308630c5,0x24e926e0,0x3c003bff,0xac0eac4d,0x300a3048,0x1bdb21e4,0x3c003c00,0xab20ab9e,0x2f1a2f97,0xa1e49bdb,0x3c003c00,
0xaa24aaa2,0x2e202e9d,0xa6e0a4e9,0x3bff3c00,0xb01cb055,0x340b3441,0x286b2a31,0x3bff3bfe,0xaf52afc5,0x333a33a8,0x1f12254d,0x3c003c00,
0xae6daee0,0x325d32cc,0xa54d9f12,0x3c003c00,0xad89adfb,0x317f31ee,0xaa31a86b,0x3bfe3bff,0xb1f8b24d,0x35c53611,0x2a632c79,0x3bfd3bfb,
0xb150b1a4,0x352c3579,0x211b27a9,0x3c003bff,0xb0a9b0fc,0x349034de,0xa7a9a11b,0x3bff3c00,0xb002b055,0x33e53441,0xac79aa63,0x3bfb3bfd,
0xb3dfb428,0x376c37ca,0x2c2e2ddc,0x3bfc3bf7,0xb2feb36e,0x36ad370d,0x22ad2902,0x3c003bfe,0xb220b28f,0x35e8364b,0xa902a2ad,0x3bfe3c00,
0xb143b1b1,0x35203584,0xaddcac2e,0x3bf73bfc,0xb4eab533,0x387e38b4,0x2d2a2f3f,0x3bf93bf3,0xb45bb4a2,0x380e3846,0x24202a31,0x3c003bfe,
0xb39db414,0x373437a9,0xaa31a420,0x3bfe3c00,0xb288b312,0x364536be,0xaf3fad2a,0x3bf33bf9,0xb5edb647,0x39363971,0x2e283052,0x3bf73bee,
0xb53db594,0x38bb38fa,0x24e92b5f,0x3c003bfd,0xb491b4e7,0x3839387b,0xab5fa4e9,0x3bfd3c00,0xb3d2b43d,0x376137eb,0xb052ae28,0x3bee3bf7,
0xb6fcb769,0x39de3a1a,0x2f263106,0x3bf33be7,0xb627b690,0x395c399e,0x25b22c47,0x3bff3bfb,0xb559b5bf,0x38cf3917,0xac47a5b2,0x3bfb3bff,
0xb491b4f4,0x38393885,0xb106af26,0x3be73bf3,0xb80cb84e,0x3a723aad,0x301231bb,0x3bf03be0,0xb71ab797,0x39ef3a32,0x267b2cde,0x3bff3bfa,
0xb627b69f,0x395c39a7,0xacdea67b,0x3bfa3bff,0xb53db5b1,0x38bb390d,0xb1bbb012,0x3be03bf0,0xb8a2b8f1,0x3af03b27,0x30923271,0x3beb3bd8,
0xb80cb856,0x3a723ab4,0x27442d76,0x3bff3bf9,0xb6fcb788,0x39de3a2a,0xad76a744,0x3bf93bff,0xb5edb673,0x3936398c,0xb271b092,0x3bd83beb,
0xb943b9a1,0x3b583b88,0x31133329,0x3be73bcf,0xb892b8e9,0x3ae43b22,0x28072e0e,0x3bff3bf7,0xb7d9b83e,0x3a533a9f,0xae0ea807,0x3bf73bff,
0xb6a2b73b,0x39a93a01,0xb329b113,0x3bcf3be7,0xb9f0ba61,0x3ba83bcd,0x319433e3,0x3be23bc5,0xb91fb985,0x3b443b7b,0x286b2ea7,0x3bff3bf5,
0xb860b8be,0x3abc3b04,0xaea7a86b,0x3bf53bff,0xb75eb806,0x3a143a6c,0xb3e3b194,0x3bc53be2,0xbaadbb33,0x3bdf3bf5,0x3216344f,0x3bdc3bba,
0xb9b6ba2e,0x3b913bbe,0x28d02f3f,0x3bff3bf3,0xb8d9b945,0x3b183b5a,0xaf3fa8d0,0x3bf33bff,0xb810b872,0x3a753acb,0xb44fb216,0x3bba3bdc,
0xbb7cbc0f,0x3bfb3c00,0x329834ae,0x3bd63bae,0xba59bae5,0x3bca3bea,0x29352fd8,0x3bfe3bf1,0xb95ab9d5,0x3b653b9e,0xafd8a935,0x3bf13bfe,
0xb875b8e4,0x3acd3b1f,0xb4aeb298,0x3bae3bd6,0xbc31bc94,0x3bfe3bee,0x331c350e,0x3bcf3ba1,0xbb09bbae,0x3bef3bfe,0x29993039,0x3bfe3bee,
0xb9e2ba70,0x3ba33bd1,0xb039a999,0x3bee3bfe,0xb8deb95c,0x3b1b3b66,0xb50eb31c,0x3ba13bcf,0xbcb3bd2c,0x3be63bbe,0x33a03570,0x3bc83b93,
0xbbcabc47,0x3bff3bfb,0x29fe3085,0x3bfe3bec,0xba73bb17,0x3bd13bf1,0xb085a9fe,0x3bec3bfe,0xb94cb9da,0x3b5d3ba0,0xb570b3a0,0x3b933bc8,
0x387238f8,0xbacbbb2c,0x38b4376f,0x3ae53b41,0x36f837e8,0xb9dbba5b,0x3b1639cf,0x39fd3a79,0x35333611,0xb8b4b94e,0x3d3b3c4d,0x38dc3973,
0x3312345b,0xb6beb80e,0x400b3e70,0x37183839,0x381e3896,0xba82bae7,0x385936e7,0x3b073b58,0x367a3756,0xb991ba10,0x3a743956,0x3a3a3aa8,
0x34d935a6,0xb871b906,0x3ca53bbf,0x393939bf,0x329c3411,0xb656b7a4,0x3ed43d99,0x380b38a7,0x37973838,0xba32ba9a,0x38013662,0x3b273b6e,
0x35ff36c7,0xb942b9bf,0x39de38e3,0x3a733ad4,0x3480353d,0xb82cb8bb,0x3c223afa,0x39913a08,0x32263390,0xb5eeb729,0x3dd73ce6,0x38853910,
0x36f837ba,0xb9dbba44,0x375835e1,0x3b453b82,0x3586363c,0xb8f0b96a,0x39523876,0x3aa93afd,0x342834d5,0xb7cab86e,0x3b5a3a46,0x39e43a4c,
0x31b132fe,0xb584b6ad,0x3d0a3c4d,0x38fa3973,0x365d370a,0xb97eb9e6,0x36b33562,0x3b613b95,0x351035b4,0xb89ab910,0x38ce380d,0x3adc3b23,
0x33a3346f,0xb73ab81e,0x3a8939a0,0x3a323a8b,0x313d326e,0xb51ab62e,0x3c5e3b8f,0x396739d1,0x35c63661,0xb91cb981,0x361334e5,0x3b7b3ba6,
0x349b352f,0xb841b8b1,0x38513750,0x3b0a3b47,0x32f8340a,0xb6a7b799,0x39cb3906,0x3a7b3ac6,0x30c931de,0xb4aeb5ae,0x3b953aa3,0x39cf3a28,
0x353335bb,0xb8b4b914,0x3577346a,0x3b923bb6,0x342834ac,0xb7cab84e,0x37b4368e,0x3b353b67,0x324d334d,0xb611b6f1,0x391c3876,0x3abe3afd,
0x30553150,0xb441b52c,0x3a9339cf,0x3a2e3a79,0x34a2351a,0xb846b8a2,0x34de33e3,0x3ba73bc5,0x336e342c,0xb70db7d0,0x36d135d2,0x3b5c3b85,
0x31a43288,0xb579b645,0x387a37db,0x3afb3b2e,0x2fc530c2,0xb3a8b4a8,0x39ae390f,0x3a863ac3,0x3414347d,0xb7a9b829,0x344832f4,0x3bba3bd1,
0x328f335b,0xb64bb6fc,0x35f6351c,0x3b7f3b9f,0x30fc31c5,0xb4deb596,0x37c336d8,0x3b333b5b,0x2ee03035,0xb2ccb423,0x38df385d,0x3ad53b06,
0x331233c5,0xb6beb756,0x336b3209,0x3bcb3bdd,0x31b13261,0xb584b622,0x3523346a,0x3b9e3bb6,0x30553103,0xb441b4e4,0x36a435e1,0x3b643b82,
0x2dfb2f52,0xb1eeb33a,0x3821376f,0x3b1c3b41,0x31ff3295,0xb5cbb651,0x324a3120,0x3bda3be6,0x30d6316a,0xb4bab543,0x34563378,0x3bb93bca,
0x2f5f3042,0xb346b42f,0x359334f3,0x3b8e3ba5,0x2d172e3b,0xb10fb22c,0x36e03637,0x3b5a3b75,0x30ef316a,0xb4d2b543,0x312d3039,0x3be63bee,
0x2ff83075,0xb3d9b460,0x331c3223,0x3bcf3bdb,0x2e152f06,0xb207b2f0,0x348c340c,0x3bb23bc1,0x2c342d24,0xb02fb11c,0x3593350e,0x3b8e3ba1,
0x2fc53042,0xb3a8b42f,0x30122ea7,0x3bf03bf5,0x2e472f06,0xb238b2f0,0x319430d2,0x3be23be9,0x2ccc2d89,0xb0c5b17f,0x331c3257,0x3bcf3bd9,
0x2aa22c0e,0xae9db00a,0x345633e3,0x3bb93bc5,0x2daf2e3b,0xb1a4b22c,0x2df52cde,0x3bf73bfa,0x2c992d24,0xb093b11c,0x30122f0c,0x3bf03bf4,
0x2b072c0e,0xaf01b00a,0x312d309f,0x3be63beb,0x28dd29f2,0xacdbadee,0x324a31bb,0x3bda3be0,0x2b392bea,0xaf33afe2,0x2b912a31,0x3bfc3bfe,
0x29d82a89,0xadd5ae84,0x2d2a2c79,0x3bf93bfb,0x28782928,0xac77ad26,0x2e8d2ddc,0x3bf53bf7,0x26302790,0xaa2fab8e,0x2ff22f3f,0x3bf03bf3,
0x263026c7,0xaa2faac5,0x267b254d,0x3bff3c00,0x25022599,0xa901a998,0x286b27a9,0x3bff3bff,0x23a9246b,0xa7a8a86b,0x29992902,0x3bfe3bfe,
0x214d227b,0xa54da67b,0x2ac82a31,0x3bfd3bfe,0xa020a084,0x24202484,0xa0529f12,0x3c003c00,0x9ead9f76,0x22ad2376,0xa1e4a11b,0x3c003c00,
0x9d1b9de4,0x211b21e4,0xa376a2ad,0x3c003c00,0x9b129c52,0x1f122052,0xa484a420,0x3c003c00,0xa928a9a6,0x2d262da3,0xa967a86b,0x3bfe3bff,
0xa82da8aa,0x2c2b2ca9,0xab5faa63,0x3bfd3bfd,0xa662a75d,0x2a612b5c,0xacacac2e,0x3bfb3bfc,0xa46ba567,0x286b2966,0xada9ad2a,0x3bf83bf9,
0xaca6ad17,0x309f310f,0xacdeabf6,0x3bfa3bfc,0xab85ac34,0x2f7e302f,0xaea7adc2,0x3bf53bf8,0xa9bfaaa2,0x2dbc2e9d,0xb039af8c,0x3bee3bf2,
0xa7f4a8dd,0x2bf22cdb,0xb120b0ac,0x3be63beb,0xaebaaf5f,0x32a73346,0xaf0cadc2,0x3bf43bf8,0xad70ae15,0x31663207,0xb0d2b02c,0x3be93bef,
0xac27accc,0x302330c5,0xb223b17a,0x3bdb3be3,0xa9bfab07,0x2dbc2f01,0xb378b2cd,0x3bca3bd3,0xb069b0d6,0x345434ba,0xb09faf8c,0x3beb3bf2,
0xaf1faff8,0x330933d9,0xb257b17a,0x3bd93be3,0xad70ae47,0x31663238,0xb40cb336,0x3bc13bce,0xab85ac99,0x2f7e3093,0xb4f3b47e,0x3ba53bb4,
0xb177b1ff,0x354f35cb,0xb1bbb0ac,0x3be03beb,0xb069b0ef,0x345434d2,0xb3e3b2cd,0x3bc53bd3,0xaebaafc5,0x32a733a8,0xb50eb47e,0x3ba13bb4,
0xaca6adaf,0x309f31a4,0xb637b5a1,0x3b753b8c,0xb288b32c,0x364536d4,0xb2dab194,0x3bd33be2,0xb143b1e5,0x352035b3,0xb4bcb413,0x3bac3bc1,
0xb002b0a2,0x33e5348a,0xb61ab569,0x3b7a3b94,0xad89aec6,0x317f32b3,0xb78db6d1,0x3b3c3b5c,0xb39db42f,0x373437d5,0xb3fdb27e,0x3bc33bd7,
0xb220b2dd,0x35e83690,0xb58cb4c3,0x3b8f3bab,0xb0a9b163,0x3490353d,0xb732b65b,0x3b4c3b6f,0xae6dafde,0x325d33c0,0xb87eb809,0x3afa3b25,
0xb45bb4cb,0x380e3866,0xb493b36b,0x3bb13bcb,0xb2feb3d9,0x36ad3767,0xb662b577,0x3b6e3b92,0xb150b226,0x352c35ee,0xb82db758,0x3b183b45,
0xaf52b07c,0x333a3466,0xb944b8b4,0x3aaf3ae5,0xb4eab56a,0x387e38dc,0xb52ab42e,0x3b9d3bbe,0xb3dfb46c,0x376c381c,0xb741b630,0x3b493b76,
0xb1f8b2ea,0x35c5369b,0xb8c9b831,0x3add3b16,0xb01cb109,0x340b34ea,0xba1eb96d,0x3a5b3a9f,0xb57cb60d,0x38e8394b,0xb5c4b4a7,0x3b873baf,
0xb462b4ed,0x38133880,0xb815b6ee,0x3b203b57,0xb2a2b3b1,0x365c3745,0xb972b8bd,0x3a9d3ae2,0xb08fb197,0x3478356d,0xbb10ba37,0x39ff3a51,
0xb611b6b5,0x394e39b4,0xb662b523,0x3b6e3b9e,0xb4d5b571,0x386e38e1,0xb88eb7b4,0x3af43b35,0xb34db43d,0x36f137eb,0xba28b952,0x3a573aa9,
0xb103b226,0x34e435ee,0xbc11bb16,0x399c39fd,0xb6aab761,0x39ae3a16,0xb705b5a1,0x3b533b8c,0xb54bb5f8,0x38c5393d,0xb90fb841,0x3ac33b10,
0xb3fab4a2,0x37833846,0xbaefb9f1,0x3a0c3a6c,0xb177b2b6,0x354f366d,0xbcb0bc08,0x393139a3,0xb747b80a,0x3a083a70,0xb7acb621,0x3b373b78,
0xb5c2b681,0x39193995,0xb997b8ac,0x3a8f3ae9,0xb454b509,0x38093895,0xbbcbba9e,0x39bb3a2a,0xb1ebb347,0x35b936eb,0xbd6bbc96,0x38c03942,
0xb7e8b866,0x3a5b3ac1,0xb82db6a4,0x3b183b64,0xb63cb70e,0x396a39e8,0xba28b91c,0x3a573abe,0xb4acb571,0x384e38e1,0xbc61bb5a,0x396539e4,
0xb261b3d9,0x36223767,0xbe4ebd3b,0x384938dc,0xb848b8c6,0x3aa83b0a,0xb886b72a,0x3af73b4d,0xb6b9b79f,0x39b73a36,0xbac3b992,0x3a1c3a91,
0xb506b5db,0x3892392a,0xbcedbc15,0x390b399a,0xb2d7b436,0x368a37e0,0xbf6abdff,0x37993871,0xb533b611,0x38b4394e,0x2ca62630,0xb09faa2f,
0xb312b45b,0x36be380e,0x31772fc5,0xb54fb3a8,0xafc5b177,0x33a8354f,0x345b3312,0xb80eb6be,0xa630aca6,0x2a2f309f,0x36113533,0xb94eb8b4,
0xb4d9b5a6,0x38713906,0x2c5a25cb,0xb055a9ca,0xb29cb411,0x365637a4,0x311c2f45,0xb4fcb32e,0xaf45b11c,0x332e34fc,0x3411329c,0xb7a4b656,
0xa5cbac5a,0x29ca3055,0x35a634d9,0xb906b871,0xb480b53d,0x382c38bb,0x2c0e2567,0xb00aa966,0xb226b390,0x35ee3729,0x30c22ec6,0xb4a8b2b3,
0xaec6b0c2,0x32b334a8,0x33903226,0xb729b5ee,0xa567ac0e,0x2966300a,0x353d3480,0xb8bbb82c,0xb428b4d5,0x37ca386e,0x2b852502,0xaf7ea901,
0xb1b1b2fe,0x358436ad,0x30692e47,0xb454b238,0xae47b069,0x32383454,0x32fe31b1,0xb6adb584,0xa502ab85,0x29012f7e,0x34d53428,0xb86eb7ca,
0xb3a3b46f,0x373a381e,0x2aee249d,0xaee8a89d,0xb13db26e,0x351a362e,0x300f2dc9,0xb3fdb1bd,0xadc9b00f,0x31bd33fd,0x326e313d,0xb62eb51a,
0xa49daaee,0x289d2ee8,0x346f33a3,0xb81eb73a,0xb2f8b40a,0x36a73799,0x2a562439,0xae52a839,0xb0c9b1de,0x34ae35ae,0x2f6c2d4a,0xb352b141,
0xad4aaf6c,0x31413352,0x31de30c9,0xb5aeb4ae,0xa439aa56,0x28392e52,0x340a32f8,0xb799b6a7,0xb24db34d,0x361136f1,0x29bf23a9,0xadbca7a8,
0xb055b150,0x3441352c,0x2eba2ccc,0xb2a7b0c5,0xacccaeba,0x30c532a7,0x31503055,0xb52cb441,0xa3a9a9bf,0x27a82dbc,0x334d324d,0xb6f1b611,
0xb1a4b288,0x35793645,0x292822df,0xad26a6df,0xafc5b0c2,0x33a834a8,0x2e082c4d,0xb1fab048,0xac4dae08,0x304831fa,0x30c22fc5,0xb4a8b3a8,
0xa2dfa928,0x26df2d26,0x328831a4,0xb645b579,0xb0fcb1c5,0x34de3596,0x28912216,0xac90a616,0xaee0b035,0x32cc3423,0x2d572b9e,0xb14daf97,
0xab9ead57,0x2f97314d,0x30352ee0,0xb423b2cc,0xa216a891,0x26162c90,0x31c530fc,0xb596b4de,0xb055b103,0x344134e4,0x27f4214d,0xabf2a54d,
0xadfbaf52,0x31ee333a,0x2ca62aa2,0xb09fae9d,0xaaa2aca6,0x2e9d309f,0x2f522dfb,0xb33ab1ee,0xa14da7f4,0x254d2bf2,0x31033055,0xb4e4b441,
0xaf5fb042,0x3346342f,0x26c72084,0xaac5a484,0xad17ae3b,0x310f322c,0x2bea29a6,0xafe2ada3,0xa9a6abea,0x2da32fe2,0x2e3b2d17,0xb22cb10f,
0xa084a6c7,0x24842ac5,0x30422f5f,0xb42fb346,0xae15af06,0x320732f0,0x25991f76,0xa998a376,0xac34ad24,0x302f311c,0x2a8928aa,0xae84aca9,
0xa8aaaa89,0x2ca92e84,0x2d242c34,0xb11cb02f,0x9f76a599,0x23762998,0x2f062e15,0xb2f0b207,0xacccad89,0x30c5317f,0x246b1de4,0xa86ba1e4,
0xaaa2ac0e,0x2e9d300a,0x2928275d,0xad26ab5c,0xa75da928,0x2b5c2d26,0x2c0e2aa2,0xb00aae9d,0x9de4a46b,0x21e4286b,0x2d892ccc,0xb17fb0c5,
0xab07ac0e,0x2f01300a,0x227b1c52,0xa67ba052,0xa8dda9f2,0x2cdb2dee,0x27902567,0xab8ea966,0xa567a790,0x29662b8e,0x29f228dd,0xadeeacdb,
0x9c52a27b,0x2052267b,0x2c0e2b07,0xb00aaf01,0xa878a928,0x2c772d26,0x2020197f,0xa4209d7f,0xa630a790,0x2a2f2b8e,0x24d022df,0xa8cfa6df,
0xa2dfa4d0,0x26df28cf,0x27902630,0xab8eaa2f,0x997fa020,0x1d7f2420,0x29282878,0xad26ac77,0xa3a9a46b,0x27a8286b,0x1b1214b6,0x9f1298b6,
0xa14da27b,0x254d267b,0x20201de4,0xa420a1e4,0x9de4a020,0x21e42420,0x227b214d,0xa67ba54d,0x94b69b12,0x18b61f12,0x246b23a9,0xa86ba7a8,
0x1d1b1de4,0xa11ba1e4,0x94b68e48,0x18b61248,0x1b121c52,0x9f12a052,0x997f97db,0x1d7f1bdb,0x17db197f,0x9bdb9d7f,0x9c529b12,0x20521f12,
0xe4814b6,0x924898b6,0x9de49d1b,0x21e4211b,0x2662275d,0xaa61ab5c,0x9de497db,0x21e41bdb,0x246b2567,0xa86ba966,0xa2dfa0e9,0x26df24e9,
0x20e922df,0xa4e9a6df,0xa567a46b,0x2966286b,0x17db1de4,0x9bdba1e4,0xa75da662,0x2b5c2a61,0x29bf2aa2,0xadbcae9d,0xa14d9b12,0x254d1f12,
0x27f428dd,0xabf2acdb,0xa630a46b,0x2a2f286b,0x246b2630,0xa86baa2f,0xa8dda7f4,0x2cdb2bf2,0x1b12214d,0x9f12a54d,0xaaa2a9bf,0x2e9d2dbc,
0x2c272ccc,0xb023b0c5,0xa3a99d1b,0x27a8211b,0x29bf2b07,0xadbcaf01,0xa878a662,0x2c772a61,0x26622878,0xaa61ac77,0xab07a9bf,0x2f012dbc,
0x1d1b23a9,0xa11ba7a8,0xacccac27,0x30c53023,0x2d702e47,0xb166b238,0xa5029ead,0x290122ad,0x2b852c99,0xaf7eb093,0xa9d8a82d,0x2dd52c2b,
0x282d29d8,0xac2badd5,0xac99ab85,0x30932f7e,0x1ead2502,0xa2ada901,0xae47ad70,0x32383166,0x2eba2fc5,0xb2a7b3a8,0xa630a020,0x2a2f2420,
0x2ca62daf,0xb09fb1a4,0xab39a928,0x2f332d26,0x29282b39,0xad26af33,0xadafaca6,0x31a4309f,0x20202630,0xa420aa2f,0xafc5aeba,0x33a832a7,
0x300230a2,0xb3e5b48a,0xa75da0e9,0x2b5c24e9,0x2d892ec6,0xb17fb2b3,0xac4daa24,0x30482e20,0x2a242c4d,0xae20b048,0xaec6ad89,0x32b3317f,
0x20e9275d,0xa4e9ab5c,0xb0a2b002,0x348a33e5,0x30a93163,0xb490b53d,0xa846a1b2,0x2c4425b2,0x2e6d2fde,0xb25db3c0,0xacfeab20,0x30f62f1a,
0x2b202cfe,0xaf1ab0f6,0xafdeae6d,0x33c0325d,0x21b22846,0xa5b2ac44,0xb163b0a9,0x353d3490,0x31503226,0xb52cb5ee,0xa8dda27b,0x2cdb267b,
0x2f52307c,0xb33ab466,0xadafac0e,0x31a4300a,0x2c0e2daf,0xb00ab1a4,0xb07caf52,0x3466333a,0x227b28dd,0xa67bacdb,0xb226b150,0x35ee352c,
0x31f832ea,0xb5c5b69b,0xa974a344,0x2d712744,0x301c3109,0xb40bb4ea,0xae61ac8c,0x32513086,0x2c8c2e61,0xb086b251,0xb109b01c,0x34ea340b,
0x23442974,0xa744ad71,0xb2eab1f8,0x369b35c5,0x32a233b1,0xb65cb745,0xaa0ba407,0x2e072806,0x308f3197,0xb478b56d,0xaf13ad0b,0x32fd3103,
0x2d0b2f13,0xb103b2fd,0xb197b08f,0x356d3478,0x24072a0b,0xa806ae07,0xb3b1b2a2,0x3745365c,0x334d343d,0xb6f1b7eb,0xaaa2a46b,0x2e9d286b,
0x31033226,0xb4e4b5ee,0xafc5ad89,0x33a8317f,0x2d892fc5,0xb17fb3a8,0xb226b103,0x35ee34e4,0x246b2aa2,0xa86bae9d,0xb43db34d,0x37eb36f1,
0x33fa34a2,0xb783b846,0xab39a4d0,0x2f3328cf,0x317732b6,0xb54fb66d,0xb03cae08,0x342931fa,0x2e08303c,0xb1fab429,0xb2b6b177,0x366d354f,
0x24d02b39,0xa8cfaf33,0xb4a2b3fa,0x38463783,0x34543509,0xb809b895,0xabd1a534,0x2fc92934,0x31eb3347,0xb5b9b6eb,0xb095ae87,0x347e3276,
0x2e873095,0xb276b47e,0xb347b1eb,0x36eb35b9,0x25342bd1,0xa934afc9,0xb509b454,0x38953809,0x34ac3571,0xb84eb8e1,0xac34a599,0x302f2998,
0x326133d9,0xb622b767,0xb0efaf06,0x34d232f0,0x2f0630ef,0xb2f0b4d2,0xb3d9b261,0x37673622,0x25992c34,0xa998b02f,0xb571b4ac,0x38e1384e,
0x350635db,0xb892b92a,0xac80a5fd,0x307a29fd,0x32d73436,0xb68ab7e0,0xb14aaf85,0x3526336b,0x2f85314a,0xb36bb526,0xb436b2d7,0x37e0368a,
0x25fd2c80,0xa9fdb07a,0xb5dbb506,0x392a3892,0,0,0,0,0,0,0,0,
0,0,0,0,0,0,0,0,0,0,0,0,
0,0,0,0,0,0,0,0,0,0,0,0,
0,0,0,0,0,0,0,0,0,0,0,0,
0,0,0,0,0,0,0,0,0,0,0,0,
0,0,0,0,0,0,0,0,0,0,0,0,
0,0,0,0,0,0,0,0,0,0,0,0,
0,0,0,0,0,0,0,0,0,0,0,0,
0,0,0,0,0,0,0,0,0,0,0,0,
0,0,0,0,0,0,0,0,0,0,0,0,
0,0,0,0,0,0,0,0,0,0,0,0,
0,0,0,0,0,0,0,0,0,0,0,0,
0,0,0,0,0,0,0,0,0,0,0,0,
0,0,0,0,0,0,0,0,0,0,0,0,
0,0,0,0,0,0,0,0,0,0,0,0,
0,0,0,0,0,0,0,0,0,0,0,0,
0,0,0,0,0,0,0,0,0,0,0,0,
0,0,0,0,0,0,0,0,0,0,0,0,
0,0,0,0,0,0,0,0,0,0,0,0,
0,0,0,0,0,0,0,0,0,0,0,0,
0,0,0,0,0,0,0,0,0,0,0,0,
0,0,0,0,0,0,0,0,0,0,0,0,
0,0,0,0,0,0,0,0,0,0,0,0,
0,0,0,0,0,0,0,0,0,0,0,0,
0,0,0,0,0,0,0,0,0,0,0,0,
0,0,0,0,0,0,0,0,0,0,0,0,
0,0,0,0,0,0,0,0,0,0,0,0,
0,0,0,0,0,0,0,0,0,0,0,0,
0,0,0,0,0,0,0,0,0,0,0,0,
0,0,0,0,0,0,0,0,0,0,0,0,
0,0,0,0,0,0,0,0,0,0,0,0,
0,0,0,0,0,0,0,0,0,0,0,0,
0,0,0,0,0,0,0,0,0,0,0,0,
0,0,0,0,0,0,0,0,0,0,0,0,
0,0,0,0,0,0,0,0,0,0,0,0,
0,0,0,0,0,0,0,0,0,0,0,0,
0,0,0,0,0,0,0,0,0,0,0,0,
0,0,0,0,0,0,0,0,0,0,0,0,
0,0,0,0,0,0,0,0,0,0,0,0,
0,0,0,0,0,0,0,0,0,0,0,0,
0,0,0,0,0,0,0,0,0,0,0,0,
0,0,0,0,0,0,0,0,0,0,0,0,
0,0,0,0,0,0,0,0,0,0,0,0,
0x2bf62c00,0x2ba82bd9,0x2b0e2b64,0x2a2f2aa7,0x2b0e2c00,0x1e462872,0xaa2fa61f,0xaba8abd9,0x29132c00,0xab0ea23e,0xa4a5ab64,0x2bf62872,
0x24a52c00,0xaa2faaa7,0x2bf6261f,0xab0e223e,0x9e462c00,0x24a5abd9,0xa78b2b64,0x2913aaa7,0xa78b2c00,0x2bf6a872,0xa913a61f,0xa4a52bd9,
0xaa2f2c00,0x278b223e,0x2ba8ab64,0x9e46a872,0xaba82c00,0xa9132aa7,0x9e46261f,0x278ba23e,0x1e460000,0x24a5223e,0x278b261f,0x29132872,
0x278b0000,0x2bf62aa7,0x29132b64,0xa4a5223e,0x2a2f0000,0x278b2bd9,0xaba8a61f,0x9e46aaa7,0x2ba80000,0xa9132872,0x1e46ab64,0x278b2bd9,
0x2bf60000,0xaba8a23e,0x2b0e261f,0xaa2fa872,0x2b0e0000,0x9e46aaa7,0xaa2f2b64,0x2ba8a23e,0x29130000,0x2b0eabd9,0xa4a5a61f,0xabf62aa7,
0x24a50000,0x2a2fa872,0x2bf6ab64,0x2b0eabd9,0x291329a8,0x278b2872,0x24a5261f,0x1e46223e,0xa4a5a9a8,0x2913223e,0x2bf62b64,0x278b2aa7,
0x9e4629a8,0xaba8aaa7,0x278ba61f,0x2a2f2bd9,0x278ba9a8,0x1e462bd9,0xa913ab64,0x2ba82872,0xaa2f29a8,0x2b0ea872,0xaba8261f,0x2bf6a23e,
0x2ba8a9a8,0xaa2fa23e,0x9e462b64,0x2b0eaaa7,0xabf629a8,0xa4a52aa7,0x2b0ea61f,0x2913abd9,0x2b0ea9a8,0x2bf6abd9,0x2a2fab64,0x24a5a872,
0x2a2f29a8,0x2b0e2aa7,0x2ba82b64,0x2bf62bd9,0xaba8a9a8,0xaa2fabd9,0x1e46a61f,0x2b0e2872,0x2bf629a8,0xa4a52872,0xab0eab64,0x2913a23e,
0xab0ea9a8,0x2bf6223e,0xaa2f261f,0x24a5aaa7,0x291329a8,0xa78baaa7,0x24a52b64,0x9e46abd9,0xa4a5a9a8,0xa9132bd9,0x2bf6a61f,0xa78ba872,
0x9e4629a8,0x2ba8a872,0x278bab64,0xaa2f223e,0x278ba9a8,0x9e46a23e,0xa913261f,0xaba82aa7,0xabf62c00,0xaba82bd9,0xab0e2b64,0xaa2f2aa7,
0xab0e2c00,0x9e462872,0x2a2fa61f,0x2ba8abd9,0xa9132c00,0x2b0ea23e,0x24a5ab64,0xabf62872,0xa4a52c00,0x2a2faaa7,0xabf6261f,0x2b0e223e,
0x1e462c00,0xa4a5abd9,0x278b2b64,0xa913aaa7,0x278b2c00,0xabf6a872,0x2913a61f,0x24a52bd9,0x2a2f2c00,0xa78b223e,0xaba8ab64,0x1e46a872,
0x2ba82c00,0x29132aa7,0x1e46261f,0xa78ba23e,0x9e460000,0xa4a5223e,0xa78b261f,0xa9132872,0xa78b0000,0xabf62aa7,0xa9132b64,0x24a5223e,
0xaa2f0000,0xa78b2bd9,0x2ba8a61f,0x1e46aaa7,0xaba80000,0x29132872,0x9e46ab64,0xa78b2bd9,0xabf60000,0x2ba8a23e,0xab0e261f,0x2a2fa872,
0xab0e0000,0x1e46aaa7,0x2a2f2b64,0xaba8a23e,0xa9130000,0xab0eabd9,0x24a5a61f,0x2bf62aa7,0xa4a50000,0xaa2fa872,0xabf6ab64,0xab0eabd9,
0xa91329a8,0xa78b2872,0xa4a5261f,0x9e46223e,0x24a5a9a8,0xa913223e,0xabf62b64,0xa78b2aa7,0x1e4629a8,0x2ba8aaa7,0xa78ba61f,0xaa2f2bd9,
0xa78ba9a8,0x9e462bd9,0x2913ab64,0xaba82872,0x2a2f29a8,0xab0ea872,0x2ba8261f,0xabf6a23e,0xaba8a9a8,0x2a2fa23e,0x1e462b64,0xab0eaaa7,
0x2bf629a8,0x24a52aa7,0xab0ea61f,0xa913abd9,0xab0ea9a8,0xabf6abd9,0xaa2fab64,0xa4a5a872,0xaa2f29a8,0xab0e2aa7,0xaba82b64,0xabf62bd9,
0x2ba8a9a8,0x2a2fabd9,0x9e46a61f,0xab0e2872,0xabf629a8,0x24a52872,0x2b0eab64,0xa913a23e,0x2b0ea9a8,0xabf6223e,0x2a2f261f,0xa4a5aaa7,
0xa91329a8,0x278baaa7,0xa4a52b64,0x1e46abd9,0x24a5a9a8,0x29132bd9,0xabf6a61f,0x278ba872,0x1e4629a8,0xaba8a872,0xa78bab64,0x2a2f223e,
0xa78ba9a8,0x1e46a23e,0x2913261f,0x2ba82aa7,0x9e460000,0xa4a5a23e,0xa78ba61f,0xa913a872,0xa78b0000,0xabf6aaa7,0xa913ab64,0x24a5a23e,
0xaa2f0000,0xa78babd9,0x2ba8261f,0x1e462aa7,0xaba80000,0x2913a872,0x9e462b64,0xa78babd9,0xabf60000,0x2ba8223e,0xab0ea61f,0x2a2f2872,
0xab0e0000,0x1e462aa7,0x2a2fab64,0xaba8223e,0xa9130000,0xab0e2bd9,0x24a5261f,0x2bf6aaa7,0xa4a50000,0xaa2f2872,0xabf62b64,0xab0e2bd9,
0x2bf62c00,0x2ba82bd9,0x2b0e2b64,0x2a2f2aa7,0x2b0e2c00,0x1e462872,0xaa2fa61f,0xaba8abd9,0x29132c00,0xab0ea23e,0xa4a5ab64,0x2bf62872,
0x24a52c00,0xaa2faaa7,0x2bf6261f,0xab0e223e,0x9e462c00,0x24a5abd9,0xa78b2b64,0x2913aaa7,0xa78b2c00,0x2bf6a872,0xa913a61f,0xa4a52bd9,
0xaa2f2c00,0x278b223e,0x2ba8ab64,0x9e46a872,0xaba82c00,0xa9132aa7,0x9e46261f,0x278ba23e,0xaa2fa9a8,0xab0eaaa7,0xaba8ab64,0xabf6abd9,
0x2ba829a8,0x2a2f2bd9,0x9e46261f,0xab0ea872,0xabf6a9a8,0x24a5a872,0x2b0e2b64,0xa913223e,0x2b0e29a8,0xabf6a23e,0x2a2fa61f,0xa4a52aa7,
0xa913a9a8,0x278b2aa7,0xa4a5ab64,0x1e462bd9,0x24a529a8,0x2913abd9,0xabf6261f,0x278b2872,0x1e46a9a8,0xaba82872,0xa78b2b64,0x2a2fa23e,
0xa78b29a8,0x1e46223e,0x2913a61f,0x2ba8aaa7,0x291329a8,0x278b2872,0x24a5261f,0x1e46223e,0xa4a5a9a8,0x2913223e,0x2bf62b64,0x278b2aa7,
0x9e4629a8,0xaba8aaa7,0x278ba61f,0x2a2f2bd9,0x278ba9a8,0x1e462bd9,0xa913ab64,0x2ba82872,0xaa2f29a8,0x2b0ea872,0xaba8261f,0x2bf6a23e,
0x2ba8a9a8,0xaa2fa23e,0x9e462b64,0x2b0eaaa7,0xabf629a8,0xa4a52aa7,0x2b0ea61f,0x2913abd9,0x2b0ea9a8,0x2bf6abd9,0x2a2fab64,0x24a5a872,
0x1e460000,0x24a5a23e,0x278ba61f,0x2913a872,0x278b0000,0x2bf6aaa7,0x2913ab64,0xa4a5a23e,0x2a2f0000,0x278babd9,0xaba8261f,0x9e462aa7,
0x2ba80000,0xa913a872,0x1e462b64,0x278babd9,0x2bf60000,0xaba8223e,0x2b0ea61f,0xaa2f2872,0x2b0e0000,0x9e462aa7,0xaa2fab64,0x2ba8223e,
0x29130000,0x2b0e2bd9,0xa4a5261f,0xabf6aaa7,0x24a50000,0x2a2f2872,0x2bf62b64,0x2b0e2bd9,0xabf62c00,0xaba82bd9,0xab0e2b64,0xaa2f2aa7,
0xab0e2c00,0x9e462872,0x2a2fa61f,0x2ba8abd9,0xa9132c00,0x2b0ea23e,0x24a5ab64,0xabf62872,0xa4a52c00,0x2a2faaa7,0xabf6261f,0x2b0e223e,
0x1e462c00,0xa4a5abd9,0x278b2b64,0xa913aaa7,0x278b2c00,0xabf6a872,0x2913a61f,0x24a52bd9,0x2a2f2c00,0xa78b223e,0xaba8ab64,0x1e46a872,
0x2ba82c00,0x29132aa7,0x1e46261f,0xa78ba23e,0x2a2fa9a8,0x2b0eaaa7,0x2ba8ab64,0x2bf6abd9,0xaba829a8,0xaa2f2bd9,0x1e46261f,0x2b0ea872,
0x2bf6a9a8,0xa4a5a872,0xab0e2b64,0x2913223e,0xab0e29a8,0x2bf6a23e,0xaa2fa61f,0x24a52aa7,0x2913a9a8,0xa78b2aa7,0x24a5ab64,0x9e462bd9,
0xa4a529a8,0xa913abd9,0x2bf6261f,0xa78b2872,0x9e46a9a8,0x2ba82872,0x278b2b64,0xaa2fa23e,0x278b29a8,0x9e46223e,0xa913a61f,0xaba8aaa7,
0xa91329a8,0xa78b2872,0xa4a5261f,0x9e46223e,0x24a5a9a8,0xa913223e,0xabf62b64,0xa78b2aa7,0x1e4629a8,0x2ba8aaa7,0xa78ba61f,0xaa2f2bd9,
0xa78ba9a8,0x9e462bd9,0x2913ab64,0xaba82872,0x2a2f29a8,0xab0ea872,0x2ba8261f,0xabf6a23e,0xaba8a9a8,0x2a2fa23e,0x1e462b64,0xab0eaaa7,
0x2bf629a8,0x24a52aa7,0xab0ea61f,0xa913abd9,0xab0ea9a8,0xabf6abd9,0xaa2fab64,0xa4a5a872,0x2ba82c00,0x29132aa7,0x1e46261f,0xa78ba23e,
0x2a2f2c00,0xa78b223e,0xaba8ab64,0x1e46a872,0x278b2c00,0xabf6a872,0x2913a61f,0x24a52bd9,0x1e462c00,0xa4a5abd9,0x278b2b64,0xa913aaa7,
0xa4a52c00,0x2a2faaa7,0xabf6261f,0x2b0e223e,0xa9132c00,0x2b0ea23e,0x24a5ab64,0xabf62872,0xab0e2c00,0x9e462872,0x2a2fa61f,0x2ba8abd9,
0xabf62c00,0xaba82bd9,0xab0e2b64,0xaa2f2aa7,0x24a50000,0x2a2f2872,0x2bf62b64,0x2b0e2bd9,0x29130000,0x2b0e2bd9,0xa4a5261f,0xabf6aaa7,
0x2b0e0000,0x9e462aa7,0xaa2fab64,0x2ba8223e,0x2bf60000,0xaba8223e,0x2b0ea61f,0xaa2f2872,0x2ba80000,0xa913a872,0x1e462b64,0x278babd9,
0x2a2f0000,0x278babd9,0xaba8261f,0x9e462aa7,0x278b0000,0x2bf6aaa7,0x2913ab64,0xa4a5a23e,0x1e460000,0x24a5a23e,0x278ba61f,0x2913a872,
0xab0ea9a8,0xabf6abd9,0xaa2fab64,0xa4a5a872,0x2bf629a8,0x24a52aa7,0xab0ea61f,0xa913abd9,0xaba8a9a8,0x2a2fa23e,0x1e462b64,0xab0eaaa7,
0x2a2f29a8,0xab0ea872,0x2ba8261f,0xabf6a23e,0xa78ba9a8,0x9e462bd9,0x2913ab64,0xaba82872,0x1e4629a8,0x2ba8aaa7,0xa78ba61f,0xaa2f2bd9,
0x24a5a9a8,0xa913223e,0xabf62b64,0xa78b2aa7,0xa91329a8,0xa78b2872,0xa4a5261f,0x9e46223e,0x278b29a8,0x9e46223e,0xa913a61f,0xaba8aaa7,
0x9e46a9a8,0x2ba82872,0x278b2b64,0xaa2fa23e,0xa4a529a8,0xa913abd9,0x2bf6261f,0xa78b2872,0x2913a9a8,0xa78b2aa7,0x24a5ab64,0x9e462bd9,
0xab0e29a8,0x2bf6a23e,0xaa2fa61f,0x24a52aa7,0x2bf6a9a8,0xa4a5a872,0xab0e2b64,0x2913223e,0xaba829a8,0xaa2f2bd9,0x1e46261f,0x2b0ea872,
0x2a2fa9a8,0x2b0eaaa7,0x2ba8ab64,0x2bf6abd9,0xaba82c00,0xa9132aa7,0x9e46261f,0x278ba23e,0xaa2f2c00,0x278b223e,0x2ba8ab64,0x9e46a872,
0xa78b2c00,0x2bf6a872,0xa913a61f,0xa4a52bd9,0x9e462c00,0x24a5abd9,0xa78b2b64,0x2913aaa7,0x24a52c00,0xaa2faaa7,0x2bf6261f,0xab0e223e,
0x29132c00,0xab0ea23e,0xa4a5ab64,0x2bf62872,0x2b0e2c00,0x1e462872,0xaa2fa61f,0xaba8abd9,0x2bf62c00,0x2ba82bd9,0x2b0e2b64,0x2a2f2aa7,
0xa4a50000,0xaa2f2872,0xabf62b64,0xab0e2bd9,0xa9130000,0xab0e2bd9,0x24a5261f,0x2bf6aaa7,0xab0e0000,0x1e462aa7,0x2a2fab64,0xaba8223e,
0xabf60000,0x2ba8223e,0xab0ea61f,0x2a2f2872,0xaba80000,0x2913a872,0x9e462b64,0xa78babd9,0xaa2f0000,0xa78babd9,0x2ba8261f,0x1e462aa7,
0xa78b0000,0xabf6aaa7,0xa913ab64,0x24a5a23e,0x9e460000,0xa4a5a23e,0xa78ba61f,0xa913a872,0x2b0ea9a8,0x2bf6abd9,0x2a2fab64,0x24a5a872,
0xabf629a8,0xa4a52aa7,0x2b0ea61f,0x2913abd9,0x2ba8a9a8,0xaa2fa23e,0x9e462b64,0x2b0eaaa7,0xaa2f29a8,0x2b0ea872,0xaba8261f,0x2bf6a23e,
0x278ba9a8,0x1e462bd9,0xa913ab64,0x2ba82872,0x9e4629a8,0xaba8aaa7,0x278ba61f,0x2a2f2bd9,0xa4a5a9a8,0x2913223e,0x2bf62b64,0x278b2aa7,
0x291329a8,0x278b2872,0x24a5261f,0x1e46223e,0xa78b29a8,0x1e46223e,0x2913a61f,0x2ba8aaa7,0x1e46a9a8,0xaba82872,0xa78b2b64,0x2a2fa23e,
0x24a529a8,0x2913abd9,0xabf6261f,0x278b2872,0xa913a9a8,0x278b2aa7,0xa4a5ab64,0x1e462bd9,0x2b0e29a8,0xabf6a23e,0x2a2fa61f,0xa4a52aa7,
0xabf6a9a8,0x24a5a872,0x2b0e2b64,0xa913223e,0x2ba829a8,0x2a2f2bd9,0x9e46261f,0xab0ea872,0xaa2fa9a8,0xab0eaaa7,0xaba8ab64,0xabf6abd9,
0xa4a50000,0xaa2fa872,0xabf6ab64,0xab0eabd9,0xa9130000,0xab0eabd9,0x24a5a61f,0x2bf62aa7,0xab0e0000,0x1e46aaa7,0x2a2f2b64,0xaba8a23e,
0xabf60000,0x2ba8a23e,0xab0e261f,0x2a2fa872,0xaba80000,0x29132872,0x9e46ab64,0xa78b2bd9,0xaa2f0000,0xa78b2bd9,0x2ba8a61f,0x1e46aaa7,
0xa78b0000,0xabf62aa7,0xa9132b64,0x24a5223e,0x9e460000,0xa4a5223e,0xa78b261f,0xa9132872,0x2ba82c00,0x29132aa7,0x1e46261f,0xa78ba23e,
0x2a2f2c00,0xa78b223e,0xaba8ab64,0x1e46a872,0x278b2c00,0xabf6a872,0x2913a61f,0x24a52bd9,0x1e462c00,0xa4a5abd9,0x278b2b64,0xa913aaa7,
0xa4a52c00,0x2a2faaa7,0xabf6261f,0x2b0e223e,0xa9132c00,0x2b0ea23e,0x24a5ab64,0xabf62872,0xab0e2c00,0x9e462872,0x2a2fa61f,0x2ba8abd9,
0xabf62c00,0xaba82bd9,0xab0e2b64,0xaa2f2aa7,0xa78ba9a8,0x1e46a23e,0x2913261f,0x2ba82aa7,0x1e4629a8,0xaba8a872,0xa78bab64,0x2a2f223e,
0x24a5a9a8,0x29132bd9,0xabf6a61f,0x278ba872,0xa91329a8,0x278baaa7,0xa4a52b64,0x1e46abd9,0x2b0ea9a8,0xabf6223e,0x2a2f261f,0xa4a5aaa7,
0xabf629a8,0x24a52872,0x2b0eab64,0xa913a23e,0x2ba8a9a8,0x2a2fabd9,0x9e46a61f,0xab0e2872,0xaa2f29a8,0xab0e2aa7,0xaba82b64,0xabf62bd9,
0xab0ea9a8,0xabf6abd9,0xaa2fab64,0xa4a5a872,0x2bf629a8,0x24a52aa7,0xab0ea61f,0xa913abd9,0xaba8a9a8,0x2a2fa23e,0x1e462b64,0xab0eaaa7,
0x2a2f29a8,0xab0ea872,0x2ba8261f,0xabf6a23e,0xa78ba9a8,0x9e462bd9,0x2913ab64,0xaba82872,0x1e4629a8,0x2ba8aaa7,0xa78ba61f,0xaa2f2bd9,
0x24a5a9a8,0xa913223e,0xabf62b64,0xa78b2aa7,0xa91329a8,0xa78b2872,0xa4a5261f,0x9e46223e,0x24a50000,0x2a2fa872,0x2bf6ab64,0x2b0eabd9,
0x29130000,0x2b0eabd9,0xa4a5a61f,0xabf62aa7,0x2b0e0000,0x9e46aaa7,0xaa2f2b64,0x2ba8a23e,0x2bf60000,0xaba8a23e,0x2b0e261f,0xaa2fa872,
0x2ba80000,0xa9132872,0x1e46ab64,0x278b2bd9,0x2a2f0000,0x278b2bd9,0xaba8a61f,0x9e46aaa7,0x278b0000,0x2bf62aa7,0x29132b64,0xa4a5223e,
0x1e460000,0x24a5223e,0x278b261f,0x29132872,0xaba82c00,0xa9132aa7,0x9e46261f,0x278ba23e,0xaa2f2c00,0x278b223e,0x2ba8ab64,0x9e46a872,
0xa78b2c00,0x2bf6a872,0xa913a61f,0xa4a52bd9,0x9e462c00,0x24a5abd9,0xa78b2b64,0x2913aaa7,0x24a52c00,0xaa2faaa7,0x2bf6261f,0xab0e223e,
0x29132c00,0xab0ea23e,0xa4a5ab64,0x2bf62872,0x2b0e2c00,0x1e462872,0xaa2fa61f,0xaba8abd9,0x2bf62c00,0x2ba82bd9,0x2b0e2b64,0x2a2f2aa7,
0x278ba9a8,0x9e46a23e,0xa913261f,0xaba82aa7,0x9e4629a8,0x2ba8a872,0x278bab64,0xaa2f223e,0xa4a5a9a8,0xa9132bd9,0x2bf6a61f,0xa78ba872,
0x291329a8,0xa78baaa7,0x24a52b64,0x9e46abd9,0xab0ea9a8,0x2bf6223e,0xaa2f261f,0x24a5aaa7,0x2bf629a8,0xa4a52872,0xab0eab64,0x2913a23e,
0xaba8a9a8,0xaa2fabd9,0x1e46a61f,0x2b0e2872,0x2a2f29a8,0x2b0e2aa7,0x2ba82b64,0x2bf62bd9,0x2b0ea9a8,0x2bf6abd9,0x2a2fab64,0x24a5a872,
0xabf629a8,0xa4a52aa7,0x2b0ea61f,0x2913abd9,0x2ba8a9a8,0xaa2fa23e,0x9e462b64,0x2b0eaaa7,0xaa2f29a8,0x2b0ea872,0xaba8261f,0x2bf6a23e,
0x278ba9a8,0x1e462bd9,0xa913ab64,0x2ba82872,0x9e4629a8,0xaba8aaa7,0x278ba61f,0x2a2f2bd9,0xa4a5a9a8,0x2913223e,0x2bf62b64,0x278b2aa7,
0x291329a8,0x278b2872,0x24a5261f,0x1e46223e,0xa02fa0f0,0x27b9279c,0x1c16190d,0x27ef27fa,0x9d4d9ed8,0x27e427d1,0x1f2e1da4,0x27cc27e0,
0x985e9b7e,0x27fb27f2,0x211a205a,0x279527b3,0x13a890e9,0x27ff2800,0x229021d7,0x274c2773,0x16939e2c,0x27fd27da,0x273927d8,0xa2e09e51,
0x242120ae,0x26da27a6,0x24c0262c,0xa670a517,0x26df25ab,0x241925a5,0x1c9f2217,0xa7eba766,0x27fe27a9,0x15fd209c,0xa16d9a6b,0xa787a7f6,
0x21bf98c2,0x277727fa,0xa583a102,0xa5cca799,0x279825ca,0x21082585,0xa7fba776,0x18a9a1c5,0x26c327f1,0xa4469bc9,0xa49da6f7,0x268a23e0,
0x1be22449,0xa7f0a6c1,0x20419d7f,0x27b627e2,0x250d15ca,0x263427fe,0xa399a73f,0x270a22c9,0x276727c1,0xa2111fe5,0x25a31c93,0x25ae27eb,
0x9a072424,0xa7f7a6d9,0x271227e9,0xa37d1cd1,0xa7d7a55a,0x9e5da5f3,0x9e1f22e5,0xa7daa738,0x26bb1d41,0x245427e4,0x27df243c,0x1db026ca,
0x234b27ba,0xa71fa029,0x19262657,0xa7f9a4e1,0xa772a1a8,0xa1dca77c,0xa800a57a,0x1084a5d5,0xa060a72c,0x27b22318,0x1b65a544,0x27f22605,
0x27be207e,0x200b27ae,0x9c61263c,0xa7eda503,0x9f7725b7,0xa7c7a59a,0xa679a75c,0x24b4a245,0xa5fba7a2,0x2550a0cc,0x273319a3,0x22fc27f8,
0x27811dee,0x218a27dd,0x950126b2,0xa7fea461,0x27fc224b,0x97c0275b,0xa731a5b9,0x2302a597,0xa67b2078,0xa4b1a7af,0x27c81b01,0x1f6b27f4,
0x2011a69a,0x27bd2485,0xa4d7245e,0xa65fa6b4,0x22ad27f8,0xa745198a,0x94cfa7a1,0x27ff20d2,0x27702400,0xa1e226ed,0x2591a4de,0x25bf2659,
0xa7f99f46,0x193fa7ca,0xa3502680,0xa71da4a9,0x27d2982b,0x1ebf27fc,0x1dbda793,0x27df2126,0xa6fe21a2,0xa3c5a77d,0x1b4c27ff,0xa7f39439,
0x262824cd,0xa51c2666,0x237726e2,0xa7132413,0xa5a0a567,0x25b0a5e6,0xa20ba740,0x2768a2c3,0x250b25f5,0xa6362557,0x2090278c,0xa7ab214f,
0xa469a673,0x26ada4bb,0x9e13a7c5,0x27db9f9c,0x24442588,0xa6c525c8,0xa7e32273,0x9d66a752,0x9890a79a,0x27fba0fc,0x279718db,0xa10e27fa,
0xa28427e1,0xa74e9d8b,0xa581a44c,0x25cfa6c0,0x2651a64c,0x24e824f0,0x203b26f8,0xa7b723db,0x1fcd262e,0xa7c22514,0x1caca7a7,0x27eaa0a8,
0x24c3a7d9,0x266e1e38,0xa6dc26a8,0xa41ea471,0xa7fd238e,0x9661a70d,0x27899a52,0xa16127f6,0x2561221d,0xa5ec2765,0xa167a5a7,0x2788a5a9,
0x987726be,0xa7fb244e,0x27299d97,0xa32427e0,0x27cda614,0x1f222534,0x1d5aa722,0x27e3a340,0xa3f1a26d,0x26f2a753,0xa7f0258a,0x9c0aa5c6,
0xa57e27f2,0xa5d19b97,0x228a23d5,0xa74d26fa,0xa2052735,0xa76922f1,0xa59e27fd,0xa5b2172a,0x2715a17e,0xa3722783,0x251e1566,0xa62627fe,
0x2466a7bf,0x26af9ffd,0x269fa7ec,0x247e1c7a,0xa6381cea,0x2508a7e8,0xa3a49f90,0x2707a7c6,0xa52a2792,0xa61c212c,0xa3569812,0x271ca7fc,
0x21e81d28,0xa76f27e5,0xa80026cd,0xf76a436,0x27f3a65b,0x9b3324dc,0xa3bf26ec,0xa7002403,0x248ba748,0x2696a2a1,0x2459946b,0xa6b727ff,
0xa6cf27d3,0xa4341ea7,0x27e6a7de,0x1d1c1dd5,0xa13124fe,0xa7912640,0x254ba701,0x25ffa3ba,0x21968ead,0xa77f2800,0x149da1ee,0x27ffa76e,
0x26eaa528,0xa406261e,0xa4d920d8,0x265da7a0,0xa7c727f8,0x9f8319bc,0x9cf620c6,0xa7e727a3,0xa6e5276b,0xa40e21ff,0x1c6e0c52,0xa7ec2800,
0xa56c263a,0xa5e22506,0x22b8a084,0xa74327ad,0xa2f62480,0xa734269d,0x2553a463,0xa5f926b0,0xa7fa27ff,0x190d93a8,0xa720274c,0x2345a290,
0xa7e027ef,0x1da49c16,0xa6bc26f0,0x2451a3f6,0xa7b327cc,0x205a9f2e,0xa6482684,0x24f5a4a4,0xa7732795,0x21d7a11a,0xa5c42608,0x258ca542,
0xa76227e9,0x22289cc5,0x25aba421,0x25a5a6da,0xa510266a,0x2632a4c8,0x27a9a6df,0x209ca419,0x9e2c22cf,0x27daa73d,0x27d8a7fe,0x9e5195fd,
0x20ae9693,0x27a6a7fd,0x262ca739,0xa51722e0,0xa61027b6,0x2539a041,0x2334a64f,0xa72524eb,0x1216227f,0x27ffa750,0xa279927b,0xa75127ff,
0x264ea32f,0x24eda726,0xa7b5260e,0xa047253b,0x27cfa7ce,0x9efd9f09,0xa68b27e2,0x249a9d72,0xa4242767,0x26d9a211,0xa7e925a3,0x9cd125ae,
0x255a9a07,0x25f3a7f7,0xa2e52712,0x2738a37d,0x273fa7d7,0xa2c99e5d,0x25e89e1f,0x2565a7da,0x9c93a399,0xa7eb270a,0x26e1a7f5,0xa4169a84,
0x9f3a26fd,0x27cba3ca,0x1d4124f7,0x27e4a646,0x27efa490,0x1c23a693,0x27baa6bb,0xa029a454,0x1406a618,0xa7ff252f,0xa1a8a34b,0xa77c271f,
0xa7fb25c1,0x1844258e,0xa72c2772,0x231821dc,0x19a32679,0x27f8a4b4,0x2718a6d2,0xa367a42e,0x26b2a733,0xa461a2fc,0xa69b978e,0xa48327fc,
0xa7041501,0xa3af27fe,0x9ae82744,0x27f4a2b2,0x8d1b26e7,0x2800a40b,0x276ca661,0xa1faa4d4,0x224b25de,0x275ba571,0xa5b9a2ad,0xa5972745,
0x2078a7fc,0xa7af17c0,0x1b012731,0x27f4a302,0xa69a267b,0x248524b1,0x245ea7c8,0xa6b49f6b,0x27f8a011,0x198aa7bd,0xa7a124d7,0x20d2265f,
0x2547252d,0x2603a61a,0xa313279e,0x272d20e4,0xa29ba6b9,0xa7492456,0x2578a694,0xa5d7a48d,0x1c2f27b1,0x27eea066,0xa6ed24fa,0x24002644,
0x1d34a800,0xa7e59020,0x27caa1e2,0x9f46a770,0x26e22469,0x2413a6ad,0x27eb1e13,0x1c86a7db,0xa740a377,0xa2c32713,0xa7fe99ee,0x959827f7,
0x278c220b,0x214fa768,0x27fd897f,0x96f8a800,0xa7c5a090,0x9f9c27ab,0xa7e81a9d,0x1cde27f5,0x27cf2329,0x1ef0a727,0x9d8ba7fb,0xa7e19890,
0xa7b512df,0x204e27ff,0x24f0274e,0x264ca284,0x25c8a3eb,0xa588a6f4,0xa752a4e8,0xa2732651,0xa0fc26c5,0x279a2444,0x27fa1d66,0x98dba7e3,
0x27f62167,0x9a39a788,0xa70f162f,0x238827fe,0xa473241c,0x26a626dd,0x1e44a66c,0xa7d8a4c5,0xa0a2a7ea,0xa7a89cb8,0x251227c3,0x26309fc0,
0x276425ef,0x2222a55e,0xa800a2da,0x8192273b,0x27531f22,0xa26da7cd,0x25c627e3,0x258a9d5a,0x1b9726f2,0x27f223f1,0xa6fa9c0a,0x23d527f0,
0xa7e0a5d1,0x9d97257e,0x9ee4a74d,0xa7d0a28a,0x2340a324,0xa722a729,0x27fa2540,0x18f4a60a,0x25f71ab6,0xa555a7f5,0x22f1a08a,0xa735a7ac,
0x25e42800,0x256a0b12,0x27832769,0x217ea205,0xa4cf19d5,0x266527f7,0x9ffd2372,0x27bf2715,0xa6d5a7db,0xa4291e07,0xa7e8a6af,0x9cea2466,
0x24038f76,0xa6eca800,0xa7eea758,0x9c3c2256,0x27ff2700,0x146ba3bf,0xa19ca642,0xa77ea4fc,0x230d26b7,0x272e2459,0x25491dc9,0xa601a7de,
0xa4ac9958,0x267f27f9,0x27ca279f,0x1f52a0de,0x1ea79c48,0xa7d3a7ee,0x1dd52406,0x27de26ea,0x26402434,0xa4fea6cf,0xa3ba9d1c,0x270127e6,
0x28002791,0xeada131,0xa76ea5ff,0x21ee254b,0x261e277f,0x25282196,0xa7a0a7ff,0xa0d8149d,0x9acfa005,0xa7f4a7be,0x27062663,0xa3a9a4d2,
0x1dfa1534,0xa7dca7fe,0x27d52782,0x9e82a184,0x236c2143,0xa716a78e,0x27f827fd,0x19bc975c,0x259c24b6,0xa5b4a677,0x276b27c7,0x21ff1f83,
0x23f62345,0x26f02720,0x26552616,0x24e32531,0x24a42451,0x268426bc,0x26c82691,0x243e2492,0x254224f5,0x26082648,0x272a26fb,0x231e23d0,
0x25d3258c,0x257c25c4,0x277b2755,0x21ae2268,0xa5f1a476,0xa55ca6a4,0xa15ba46e,0x278a26a9,0xa7c4a710,0x9fb4a383,0x1cc59a20,0x27e927f7,
0xa7c1a800,0x1fd904b6,0x24c82228,0x266a2762,0xa5eaa70c,0x25632393,0x273d2632,0x22cf2510,0x27502539,0x227f2610,0xa7ffa725,0x927ba334,
0x272627ff,0xa32f9216,0xa53ba751,0x260e2279,0x1f0924ed,0xa7cea64e,0x1d72a047,0x27e227b5,0xa4eb9efd,0xa64fa7cf,0x26f5249a,0x23e6268b,
0xa7f5a5e8,0x9a84a565,0xa0962173,0xa7aaa786,0xa22ea6e1,0x27612416,0xa800a668,0x87dba4ca,0x262a1fa8,0x251927c5,0xa0b4a672,0x27a624be,
0x26ab27fd,0xa46b16c5,0x26a22155,0x2478278b,0x27d12682,0x9ecc24a7,0x269327cb,0xa4901f3a,0xa0ea23fb,0xa79da6ef,0xa52f1c23,0xa618a7ef,
0xa756a74b,0x2262a296,0xa58ea7ff,0x25c19406,0x23caa120,0x26fd2794,0x26461844,0x24f727fb,0xa6e7a704,0x240ba3af,0x26619ae8,0x24d427f4,
0x26d28d1b,0x242e2800,0x1d03276c,0xa7e7a1fa,0x178e2718,0xa7fca367,0xa78fa622,0x213da523,0xa744a69b,0x22b2a483,0x25e09e8e,0x256e27d5,
0x254e276d,0xa5fd21f4,0xa137a800,0x27900de4,0xa7e6a3b4,0x1d0fa703,0x26d0263e,0xa4312501,0x26e99de2,0x240927dd,0xa7ed9e9b,0x9c55a7d4,
0xa1902620,0xa780a525,0x2571a361,0x25de2719,0xa25ca7ba,0x2757a023,0xa8009c2f,0x9020a7ee,0x252d26cb,0xa61a2439,0x279e9d34,0x20e427e5,
0xa6b9a547,0x2456a603,0xa6942313,0xa48da72d,0x27b1229b,0xa0662749,0x24faa578,0x264425d7,0x19ee27eb,0xa7f71c86,0xa0ba27c0,0xa7a59ff1,
0x97fa7fe,0x28009598,0x2234a785,0x27602179,0x9a9d27fd,0xa7f596f8,0xa39e2737,0xa709a2eb,0x1e69a7e8,0x27d61cde,0x247ba6d7,0x26a12426,
0x1f15a7ff,0x27cd91b2,0x268821cb,0xa49f2775,0xa53d2723,0xa60ca33a,0xa329a612,0x2727a536,0x2778a497,0x21b9268d,0x92df27cf,0xa7ff1ef0,
0xa7f01bb0,0x1bfba7f1,0x23eba7b5,0x26f4204e,0xa41c27f6,0xa6dd9a39,0x266ca70f,0x24c52388,0x27eaa473,0x1cb826a6,0xa7c31e44,0x1fc0a7d8,
0xa5efa0a2,0x255ea7a8,0x22da2512,0xa73b2630,0x962f2764,0xa7fe2222,0x22d4a800,0x273c8192,0x260aa7d0,0x25401ee4,0xa114a495,0x2796a68f,
0xa6c618f4,0x2441a7fa,0xa686279b,0xa4a2a0f6,0xa0352774,0xa7b821d1,0x2653114d,0xa4e62800,0x27ffa4f2,0x1344264a,0x21b3a7b4,0x277aa054,
0xa75f278d,0xa23aa149,0xa80025f7,0x8b12a555,0x20c022be,0xa7a42741,0x99d525e4,0xa7f7256a,0x27d6a6e4,0x1e762411,0x27dba4cf,0x9e072665,
0x9ab6a4b9,0x27f5a675,0x208aa6d5,0x27aca429,0x27f9a72e,0x1958230d,0xa0de2601,0xa79f2549,0x2256a67f,0x2758a4ac,0x25939f52,0xa5bd27ca,
0xa4fc1c3c,0x2642a7ee,0x27b0a7bb,0x206c201d,0xa7de277e,0x9dc9a19c,0x1eb3a575,0x27d3a5d9,0xa7c926b6,0x1f5fa45c,0x267da488,0xa4ae2698,
0xa73027f3,0xa3071b1a,0x27fca7af,0x17f22072,0xa2a72595,0xa74725bb,0x25dba75a,0x2573a251,0x20171971,0xa7bc27f9,0x1c48a35c,0x27eea71b,
0x26d4a624,0xa42c2521,0x2677a716,0x24b6a36c,0x27bea75d,0xa005223f,0x24d2a5b4,0x2663a59c,0x27fea7f4,0x15341acf,0x2184a3a9,0x2782a706,
0x278ea7dc,0x21439dfa,0x175c9e82,0x27fda7d5,0xa531257c,0x2616a5d3,0xa0f021ae,0x279ca77b,0xa49224e3,0x2691a655,0x9ed8202f,0x27d1a7b9,
0xa3d0243e,0x26fba6c8,0x9b7e1d4d,0x27f2a7e4,0xa268231e,0x2755a72a,0x90e9185e,0x2800a7fb,0x2217a4c0,0xa7662670,0xa80027c4,0x4b61fb4,
0x9a6b9c9f,0xa7f627eb,0xa70c27c1,0x23939fd9,0xa476216d,0xa6a42787,0xa46e25ea,0x26a9a563,0xa71025f1,0xa383255c,0x9a20215b,0x27f7a78a,
0x98c223e6,0x27faa6f5,0xa1029be2,0xa79927f0,0x25caa1bf,0x2585a777,0xa7762583,0xa1c525cc,0x27f1a798,0x9bc9a108,0xa6f727fb,0x23e098a9,
0x2449a6c3,0xa6c12446,0x9d7f249d,0x27e2a68a,0x9fa8a22e,0xa7c52761,0x2672a800,0xa4be87db,0xa7fd262a,0x96c52519,0xa155a0b4,0xa78b27a6,
0xa17326ab,0x2786a46b,0xa7fe26a2,0x15ca2478,0x2668a096,0x24caa7aa,0x9fe52634,0x27c1a50d,0x243c2060,0x26caa7b2,0x26829b65,0x24a7a7f2,
0x2657a7df,0xa4e19db0,0x23fba7d1,0xa6ef1ecc,0xa57a9926,0xa5d527f9,0xa74b20ea,0xa296279d,0xa5442800,0x26059084,0xa1202756,0x2794a262,
0xa6229d03,0xa52327e7,0xa0cc27c7,0x27a29f77,0x9e8e278f,0x27d5a13d,0x27dda550,0x9deea5fb,0x27aea5e0,0xa07ea56e,0xa503a18a,0xa63c2781,
0xa59aa00b,0xa5b727be,0xa24527ed,0x275c9c61,0x276d14cf,0x21f4a7ff,0xa8002190,0xde42780,0xa3b4a54e,0xa70325fd,0x263e2137,0x2501a790,
0x9de227e6,0x27dd9d0f,0x9e9ba6d0,0xa7d42431,0x2620a6e9,0xa525a409,0xa36127ed,0x27191c55,0xa7fc193f,0x982b27f9,0xa126a71d,0xa7932350,
0x277d1ebf,0x21a2a7d2,0x143927df,0x27ff9dbd,0xa659a3c5,0xa4de26fe,0x2023a7f3,0xa7ba9b4c,0x24a925bf,0x2680a591,0xa4392757,0x26cb225c,
0x27c09e69,0x9ff1a7d6,0x2666a47b,0xa4cda6a1,0xa78520ba,0x217927a5,0xa5e6251c,0x25672628,0x2737a234,0xa2eba760,0x2557a5b0,0xa5f5a5a0,
0xa6d7239e,0x24262709,0xa4bb2636,0x2673250b,0xa6c0210e,0x244c2797,0x268d260c,0x2497a53d,0x23dba5cf,0xa6f8a581,0xa7f1a1b9,0x9bb02778,
0x91b227b7,0x27ff203b,0x27759bfb,0xa1cba7f0,0xa33aa7cd,0xa7231f15,0xa536249f,0x26122688,0x2514a2d4,0xa62ea73c,0xa0a825ec,0x27a72561,
0x1e3827c2,0x27d91fcd,0xa471a7ea,0xa6a81cac,0xa70da66e,0xa38e24c3,0x27f6241e,0x1a52a6dc,0x27651661,0xa21da7fd,0xa5a92161,0x25a72789,
0xa1d12441,0x277426c6,0xa800a4a2,0x114d2686,0xa64aa7b8,0xa4f22035,0x2054a4e6,0xa7b4a653,0x268f1344,0xa495a7ff,0x26be277a,0x244ea1b3,
0x20f62796,0x279b2114,0xa6141877,0x253427fb,0x172aa508,0xa7fda638,0xa149a707,0xa78da3a4,0x27fe25b2,0x9566a59e,0x2741223a,0xa2bea75f,
0x1c7a2626,0x27ec251e,0x241127a4,0x26e420c0,0xa7c6a47e,0x1f90269f,0xa6759e76,0x24b927d6,0x201d25bd,0x27bb2593,0x265b21e8,0xa4dca76f,
0xa5d9a06c,0x257527b0,0x274827f3,0x22a19b33,0xa792a7d3,0xa12c1eb3,0x1812248b,0x27fc2696,0x9d28a52a,0xa7e5a61c,0xa6cda356,0x2436271c,
0xa45ca65d,0xa6b6a4d9,0x269827bc,0x24882017,0x1b1a9f5f,0xa7f3a7c9,0x207224ae,0x27af267d,0x25bb2307,0xa595a730,0xa25197f2,0x275a27fc,
0x27f92747,0x9971a2a7,0xa71ba573,0x235c25db,0x263a26e5,0x2506240e,0xa0849c6e,0x27ad27ec,0x2480256c,0x269d25e2,0xa463a2b8,0x26b02743,
0x20c622f6,0x27a32734,0xa624a553,0x252125f9,0xc521cf6,0x280027e7,0xa75da6d4,0x223f242c,
};

#define PROF(slot) do {} while (0)
#define PROF3(slot) do {} while (0)
#define PROF2(slot) do {} while (0)

__device__ __forceinline__ uint32_t smem_u32(const void* p) { return (uint32_t)__cvta_generic_to_shared(p); }

__device__ __forceinline__ void mbar_init(uint32_t a, uint32_t c) {
  asm volatile("mbarrier.init.shared::cta.b64 [%0], %1;\n" ::"r"(a), "r"(c) : "memory");
}
__device__ __forceinline__ void mbar_expect_tx(uint32_t a, uint32_t bytes) {
  asm volatile("mbarrier.arrive.expect_tx.shared::cta.b64 _, [%0], %1;\n" ::"r"(a), "r"(bytes) : "memory");
}
__device__ __forceinline__ void mbar_arrive_cluster(uint32_t cluster_addr) {
  asm volatile("mbarrier.arrive.shared::cluster.b64 _, [%0];\n" ::"r"(cluster_addr) : "memory");
}
__device__ __forceinline__ void mbar_arrive_cluster_n(uint32_t cluster_addr, uint32_t n) {
  asm volatile("mbarrier.arrive.shared::cluster.b64 _, [%0], %1;\n" ::"r"(cluster_addr), "r"(n) : "memory");
}
__device__ __forceinline__ bool mbar_try(uint32_t a, uint32_t parity) {
  uint32_t ok;
  asm volatile("{\n.reg .pred p;\nmbarrier.try_wait.parity.shared::cta.b64 p, [%1], %2;\nselp.u32 %0, 1, 0, p;\n}\n"
               : "=r"(ok) : "r"(a), "r"(parity) : "memory");
  return ok;
}
__device__ __forceinline__ void mbar_wait(uint32_t a, uint32_t parity) {
  if (mbar_try(a, parity)) return;
#pragma unroll 1
  for (int n = 0; n < SPIN_LIMIT; n++)
    if (mbar_try(a, parity)) break;
}
__device__ __forceinline__ void mbar_wait_idle(uint32_t a, uint32_t parity) {
#pragma unroll 1
  for (int n = 0; n < SPIN_LIMIT; n++) {
    uint32_t ok;
    asm volatile("{\n.reg .pred p;\nmbarrier.try_wait.parity.shared::cta.b64 p, [%1], %2, %3;\nselp.u32 %0, 1, 0, p;\n}\n"
                 : "=r"(ok) : "r"(a), "r"(parity), "r"(4000) : "memory");
    if (ok) break;
  }
}
__device__ __forceinline__ bool elect_one() {
  uint32_t p;
  asm volatile("{\n.reg .pred P;\nelect.sync _|P, 0xffffffff;\nselp.u32 %0, 1, 0, P;\n}\n" : "=r"(p));
  return p;
}
__device__ __forceinline__ uint32_t mapa(uint32_t a, uint32_t rank) {
  uint32_t r;
  asm volatile("mapa.shared::cluster.u32 %0, %1, %2;\n" : "=r"(r) : "r"(a), "r"(rank));
  return r;
}
__device__ __forceinline__ void nb_sync(int id, int n) { asm volatile("bar.sync %0, %1;\n" ::"r"(id), "r"(n) : "memory"); }
__device__ __forceinline__ void nb_arrive(int id, int n) { asm volatile("bar.arrive %0, %1;\n" ::"r"(id), "r"(n) : "memory"); }
__device__ __forceinline__ void cluster_sync_all() {
  asm volatile("barrier.cluster.arrive.relaxed.aligned;\nbarrier.cluster.wait.aligned;\n" ::: "memory");
}
__device__ __forceinline__ void fence_async_smem() { asm volatile("fence.proxy.async.shared::cta;\n" ::: "memory"); }
__device__ __forceinline__ void fence_async_all() { asm volatile("fence.proxy.async.global;\n" ::: "memory"); }

__device__ __forceinline__ void tma_load_3d(uint32_t dst, const CUtensorMap* tm, uint32_t bar, int c0, int c1, int c2) {
  asm volatile(
      "cp.async.bulk.tensor.3d.shared::cluster.global.mbarrier::complete_tx::bytes [%0], [%1, {%3, %4, %5}], [%2];\n"
      ::"r"(dst), "l"(tm), "r"(bar), "r"(c0), "r"(c1), "r"(c2) : "memory");
}
__device__ __forceinline__ void tma_load_4d(uint32_t dst, const CUtensorMap* tm, uint32_t bar, int c0, int c1, int c2, int c3) {
  asm volatile(
      "cp.async.bulk.tensor.4d.shared::cluster.global.mbarrier::complete_tx::bytes [%0], [%1, {%3, %4, %5, %6}], [%2];\n"
      ::"r"(dst), "l"(tm), "r"(bar), "r"(c0), "r"(c1), "r"(c2), "r"(c3) : "memory");
}
__device__ __forceinline__ void tma_load_3d_mc(uint32_t dst, const CUtensorMap* tm, uint32_t bar, int c0, int c1, int c2) {
  asm volatile(
      "cp.async.bulk.tensor.3d.shared::cluster.global.mbarrier::complete_tx::bytes.multicast::cluster [%0], [%1, {%3, %4, %5}], [%2], %6;\n"
      ::"r"(dst), "l"(tm), "r"(bar), "r"(c0), "r"(c1), "r"(c2), "h"((uint16_t)3) : "memory");
}
__device__ __forceinline__ void tma_load_5d(uint32_t dst, const CUtensorMap* tm, uint32_t bar, int c0, int c4) {
  asm volatile(
      "cp.async.bulk.tensor.5d.shared::cluster.global.mbarrier::complete_tx::bytes [%0], [%1, {%3, %5, %5, %5, %4}], [%2];\n"
      ::"r"(dst), "l"(tm), "r"(bar), "r"(c0), "r"(c4), "r"(0) : "memory");
}
__device__ __forceinline__ void bulk_load(uint32_t dst, const void* src, uint32_t bytes, uint32_t bar) {
  asm volatile("cp.async.bulk.shared::cluster.global.mbarrier::complete_tx::bytes [%0], [%1], %2, [%3];\n"
               ::"r"(dst), "l"(src), "r"(bytes), "r"(bar) : "memory");
}
__device__ __forceinline__ void bulk_commit() { asm volatile("cp.async.bulk.commit_group;\n" ::: "memory"); }
__device__ __forceinline__ void bulk_wait0() { asm volatile("cp.async.bulk.wait_group 0;\n" ::: "memory"); }
__device__ __forceinline__ void prefetch_tmap(const CUtensorMap* tm) {
  asm volatile("prefetch.tensormap [%0];\n" ::"l"(tm) : "memory");
}

__device__ __forceinline__ void wg_fence() { asm volatile("wgmma.fence.sync.aligned;\n" ::: "memory"); }
__device__ __forceinline__ void wg_commit() { asm volatile("wgmma.commit_group.sync.aligned;\n" ::: "memory"); }
template <int N> __device__ __forceinline__ void wg_wait() {
  asm volatile("wgmma.wait_group.sync.aligned %0;\n" ::"n"(N) : "memory");
}
__device__ __forceinline__ uint64_t mkdesc(uint32_t addr, uint32_t lbo, uint32_t sbo, uint32_t swz) {
  return (uint64_t)((addr & 0x3FFFF) >> 4) | ((uint64_t)(lbo >> 4) << 16) | ((uint64_t)(sbo >> 4) << 32) |
         ((uint64_t)swz << 62);
}

#define R4(d, o) "+f"(d[o + 0]), "+f"(d[o + 1]), "+f"(d[o + 2]), "+f"(d[o + 3])
#define R8(d, o) R4(d, o), R4(d, o + 4)
#define R16(d, o) R8(d, o), R8(d, o + 8)
#define R32(d, o) R16(d, o), R16(d, o + 16)
#define R64(d, o) R32(d, o), R32(d, o + 32)

__device__ __forceinline__ void wgmma_n192(float (&d)[96], uint64_t da, uint64_t db, uint32_t acc) {
  asm volatile(
      "{\n.reg .pred p;\nsetp.ne.u32 p, %98, 0;\n"
      "wgmma.mma_async.sync.aligned.m64n192k16.f32.bf16.bf16 "
      "{%0,%1,%2,%3,%4,%5,%6,%7,%8,%9,%10,%11,%12,%13,%14,%15,%16,%17,%18,%19,%20,%21,%22,%23,%24,%25,%26,%27,%28,%29,%30,%31,"
      "%32,%33,%34,%35,%36,%37,%38,%39,%40,%41,%42,%43,%44,%45,%46,%47,%48,%49,%50,%51,%52,%53,%54,%55,%56,%57,%58,%59,%60,%61,%62,%63,"
      "%64,%65,%66,%67,%68,%69,%70,%71,%72,%73,%74,%75,%76,%77,%78,%79,%80,%81,%82,%83,%84,%85,%86,%87,%88,%89,%90,%91,%92,%93,%94,%95}, "
      "%96, %97, p, 1, 1, 0, 1;\n}\n"
      : R64(d, 0), R32(d, 64)
      : "l"(da), "l"(db), "r"(acc));
}
__device__ __forceinline__ void wgmma_n128(float (&d)[64], uint64_t da, uint64_t db, uint32_t acc) {
  asm volatile(
      "{\n.reg .pred p;\nsetp.ne.u32 p, %66, 0;\n"
      "wgmma.mma_async.sync.aligned.m64n128k16.f32.bf16.bf16 "
      "{%0,%1,%2,%3,%4,%5,%6,%7,%8,%9,%10,%11,%12,%13,%14,%15,%16,%17,%18,%19,%20,%21,%22,%23,%24,%25,%26,%27,%28,%29,%30,%31,"
      "%32,%33,%34,%35,%36,%37,%38,%39,%40,%41,%42,%43,%44,%45,%46,%47,%48,%49,%50,%51,%52,%53,%54,%55,%56,%57,%58,%59,%60,%61,%62,%63}, "
      "%64, %65, p, 1, 1, 0, 1;\n}\n"
      : R64(d, 0)
      : "l"(da), "l"(db), "r"(acc));
}
template <int N> __device__ __forceinline__ void fence_regs(float (&d)[N]) {
#pragma unroll
  for (int i = 0; i < N; i++) asm volatile("" : "+f"(d[i])::"memory");
}

__device__ __forceinline__ void mma16816(float (&d)[4], uint32_t a0, uint32_t a1, uint32_t a2, uint32_t a3, uint32_t b0,
                                         uint32_t b1) {
  asm("mma.sync.aligned.m16n8k16.row.col.f32.bf16.bf16.f32 {%0,%1,%2,%3}, {%4,%5,%6,%7}, {%8,%9}, {%0,%1,%2,%3};\n"
      : "+f"(d[0]), "+f"(d[1]), "+f"(d[2]), "+f"(d[3])
      : "r"(a0), "r"(a1), "r"(a2), "r"(a3), "r"(b0), "r"(b1));
}
__device__ __forceinline__ void mma16816_z(float (&d)[4], uint32_t a0, uint32_t a1, uint32_t a2, uint32_t a3, uint32_t b0,
                                           uint32_t b1) {
  asm("mma.sync.aligned.m16n8k16.row.col.f32.bf16.bf16.f32 {%0,%1,%2,%3}, {%4,%5,%6,%7}, {%8,%9}, {%10,%10,%10,%10};\n"
      : "=f"(d[0]), "=f"(d[1]), "=f"(d[2]), "=f"(d[3])
      : "r"(a0), "r"(a1), "r"(a2), "r"(a3), "r"(b0), "r"(b1), "f"(0.f));
}
__device__ __forceinline__ void ldsm4t(uint32_t (&r)[4], uint32_t a) {
  asm volatile("ldmatrix.sync.aligned.m8n8.x4.trans.shared.b16 {%0,%1,%2,%3}, [%4];\n"
               : "=r"(r[0]), "=r"(r[1]), "=r"(r[2]), "=r"(r[3]) : "r"(a) : "memory");
}
__device__ __forceinline__ void ldsm2t(uint32_t& r0, uint32_t& r1, uint32_t a) {
  asm volatile("ldmatrix.sync.aligned.m8n8.x2.trans.shared.b16 {%0,%1}, [%2];\n" : "=r"(r0), "=r"(r1) : "r"(a) : "memory");
}
__device__ __forceinline__ void st_async128(uint32_t a, uint32_t bar, uint32_t x, uint32_t y, uint32_t z, uint32_t w) {
  asm volatile("st.async.weak.shared::cluster.mbarrier::complete_tx::bytes.v4.b32 [%0], {%2,%3,%4,%5}, [%1];\n"
               ::"r"(a), "r"(bar), "r"(x), "r"(y), "r"(z), "r"(w) : "memory");
}
__device__ __forceinline__ void mbar_arrive(uint32_t a) {
  asm volatile("mbarrier.arrive.shared::cta.b64 _, [%0];\n" ::"r"(a) : "memory");
}
__device__ __forceinline__ void stsm4(uint32_t a, uint32_t r0, uint32_t r1, uint32_t r2, uint32_t r3) {
  asm volatile("stmatrix.sync.aligned.m8n8.x4.shared.b16 [%0], {%1,%2,%3,%4};\n"
               ::"r"(a), "r"(r0), "r"(r1), "r"(r2), "r"(r3) : "memory");
}
__device__ __forceinline__ void stsm4t(uint32_t a, uint32_t r0, uint32_t r1, uint32_t r2, uint32_t r3) {
  asm volatile("stmatrix.sync.aligned.m8n8.x4.trans.shared.b16 [%0], {%1,%2,%3,%4};\n"
               ::"r"(a), "r"(r0), "r"(r1), "r"(r2), "r"(r3) : "memory");
}
__device__ __forceinline__ uint2 lds64(uint32_t a) {
  uint2 v;
  asm volatile("ld.shared.v2.u32 {%0,%1}, [%2];\n" : "=r"(v.x), "=r"(v.y) : "r"(a));
  return v;
}
__device__ __forceinline__ uint4 lds128(uint32_t a) {
  uint4 v;
  asm volatile("ld.shared.v4.u32 {%0,%1,%2,%3}, [%4];\n" : "=r"(v.x), "=r"(v.y), "=r"(v.z), "=r"(v.w) : "r"(a) : "memory");
  return v;
}
__device__ __forceinline__ void sts128(uint32_t a, uint32_t x, uint32_t y, uint32_t z, uint32_t w) {
  asm volatile("st.shared.v4.u32 [%0], {%1,%2,%3,%4};\n" ::"r"(a), "r"(x), "r"(y), "r"(z), "r"(w) : "memory");
}
__device__ __forceinline__ uint32_t pack_bf16(float lo, float hi) {
  uint32_t r;
  asm("cvt.rn.bf16x2.f32 %0, %1, %2;\n" : "=r"(r) : "f"(hi), "f"(lo));
  return r;
}
__device__ __forceinline__ uint32_t bmul2(uint32_t a, uint32_t b) {
  uint32_t r;
  asm("mul.rn.bf16x2 %0, %1, %2;\n" : "=r"(r) : "r"(a), "r"(b));
  return r;
}
__device__ __forceinline__ uint32_t bmax2(uint32_t a, uint32_t b) {
  uint32_t r;
  asm("max.bf16x2 %0, %1, %2;\n" : "=r"(r) : "r"(a), "r"(b));
  return r;
}
__device__ __forceinline__ uint32_t bfma2(uint32_t a, uint32_t b, uint32_t c) {
  uint32_t r;
  asm("fma.rn.bf16x2 %0, %1, %2, %3;\n" : "=r"(r) : "r"(a), "r"(b), "r"(c));
  return r;
}
__device__ __forceinline__ void prefetch_l2(const void* p) { asm volatile("prefetch.global.L2 [%0];\n" ::"l"(p)); }
__device__ __forceinline__ void cp_async16n(uint32_t dst, const void* src) {
  asm volatile("cp.async.cg.shared.global [%0], [%1], 16;\n" ::"r"(dst), "l"(src) : "memory");
}
__device__ __forceinline__ void cp_async16(uint32_t dst, const void* src, uint32_t srcbytes) {
  asm volatile("cp.async.cg.shared.global.L2::256B [%0], [%1], 16, %2;\n" ::"r"(dst), "l"(src), "r"(srcbytes) : "memory");
}
__device__ __forceinline__ uint32_t ld_acquire(const uint32_t* p) {
  uint32_t v;
  asm volatile("ld.acquire.gpu.global.u32 %0, [%1];\n" : "=r"(v) : "l"(p) : "memory");
  return v;
}
__device__ __forceinline__ uint32_t ld_relaxed(const uint32_t* p) {
  uint32_t v;
  asm volatile("ld.relaxed.gpu.global.u32 %0, [%1];\n" : "=r"(v) : "l"(p) : "memory");
  return v;
}
__device__ __forceinline__ void st_release(uint32_t* p, uint32_t v) {
  asm volatile("st.release.gpu.global.u32 [%0], %1;\n" ::"l"(p), "r"(v) : "memory");
}
__device__ __forceinline__ void wait_flag(const uint32_t* p, uint32_t want) {
  int n = 0;
  while (ld_relaxed(p) != want && ++n < SPIN_LIMIT) __nanosleep(40);
  (void)ld_acquire(p);
}

struct Params {
  const __nv_bfloat16* x;
  const __nv_bfloat16* w;
  const __nv_bfloat16* q;
  const __nv_bfloat16* k;
  const __nv_bfloat16* v;
  const __nv_bfloat16* shift_k;
  const __nv_bfloat16* ssm_k;
  const __nv_bfloat16* ssm_D;
  const __nv_bfloat16* wo;
  __nv_bfloat16* out;
};

#define U4(c, d, o) c(d[o + 0]), c(d[o + 1]), c(d[o + 2]), c(d[o + 3])
#define U8(c, d, o) U4(c, d, o), U4(c, d, o + 4)
#define U16(c, d, o) U8(c, d, o), U8(c, d, o + 8)
#define U32(c, d, o) U16(c, d, o), U16(c, d, o + 16)
#define D32 "{%0,%1,%2,%3,%4,%5,%6,%7,%8,%9,%10,%11,%12,%13,%14,%15,%16,%17,%18,%19,%20,%21,%22,%23,%24,%25,%26,%27,%28,%29,%30,%31}"
#define D16 "{%0,%1,%2,%3,%4,%5,%6,%7,%8,%9,%10,%11,%12,%13,%14,%15}"
#define D8 "{%0,%1,%2,%3,%4,%5,%6,%7}"
template <int ACC> __device__ __forceinline__ void hmma_n128t(uint32_t (&d)[32], const uint32_t (&a)[4], uint64_t db) {
  if (ACC)
    asm volatile("wgmma.mma_async.sync.aligned.m64n128k16.f16.f16.f16 " D32 ", {%32,%33,%34,%35}, %36, 1, 1, 1, 1;\n"
                 : U32("+r", d, 0) : "r"(a[0]), "r"(a[1]), "r"(a[2]), "r"(a[3]), "l"(db));
  else
    asm volatile("wgmma.mma_async.sync.aligned.m64n128k16.f16.f16.f16 " D32 ", {%32,%33,%34,%35}, %36, 0, 1, 1, 1;\n"
                 : U32("=r", d, 0) : "r"(a[0]), "r"(a[1]), "r"(a[2]), "r"(a[3]), "l"(db));
}
template <int ACC, int TB> __device__ __forceinline__ void hmma_n32(uint32_t (&d)[8], const uint32_t (&a)[4], uint64_t db) {
  if (ACC)
    asm volatile("wgmma.mma_async.sync.aligned.m64n32k16.f16.f16.f16 " D8 ", {%8,%9,%10,%11}, %12, 1, 1, 1, %13;\n"
                 : U8("+r", d, 0) : "r"(a[0]), "r"(a[1]), "r"(a[2]), "r"(a[3]), "l"(db), "n"(TB));
  else
    asm volatile("wgmma.mma_async.sync.aligned.m64n32k16.f16.f16.f16 " D8 ", {%8,%9,%10,%11}, %12, 0, 1, 1, %13;\n"
                 : U8("=r", d, 0) : "r"(a[0]), "r"(a[1]), "r"(a[2]), "r"(a[3]), "l"(db), "n"(TB));
}
template <int ACC> __device__ __forceinline__ void hmma_n64t(uint32_t (&d)[16], const uint32_t (&a)[4], uint64_t db) {
  if (ACC)
    asm volatile("wgmma.mma_async.sync.aligned.m64n64k16.f16.f16.f16 " D16 ", {%16,%17,%18,%19}, %20, 1, 1, 1, 1;\n"
                 : U16("+r", d, 0) : "r"(a[0]), "r"(a[1]), "r"(a[2]), "r"(a[3]), "l"(db));
  else
    asm volatile("wgmma.mma_async.sync.aligned.m64n64k16.f16.f16.f16 " D16 ", {%16,%17,%18,%19}, %20, 0, 1, 1, 1;\n"
                 : U16("=r", d, 0) : "r"(a[0]), "r"(a[1]), "r"(a[2]), "r"(a[3]), "l"(db));
}
template <int N> __device__ __forceinline__ void fence_regs(uint32_t (&d)[N]) {
#pragma unroll
  for (int i = 0; i < N; i++) asm volatile("" : "+r"(d[i])::"memory");
}
__device__ __forceinline__ uint32_t hmul(uint32_t a, uint32_t b) { uint32_t r; asm("mul.rn.f16x2 %0, %1, %2;\n" : "=r"(r) : "r"(a), "r"(b)); return r; }
__device__ __forceinline__ uint32_t hfma(uint32_t a, uint32_t b, uint32_t c) { uint32_t r; asm("fma.rn.f16x2 %0, %1, %2, %3;\n" : "=r"(r) : "r"(a), "r"(b), "r"(c)); return r; }
__device__ __forceinline__ uint32_t hfnma(uint32_t a, uint32_t b, uint32_t c) {
  uint32_t r;
  asm("{\n.reg .b32 t;\nneg.f16x2 t, %1;\nfma.rn.f16x2 %0, t, %2, %3;\n}\n" : "=r"(r) : "r"(a), "r"(b), "r"(c));
  return r;
}
__device__ __forceinline__ void rot(uint32_t xr, uint32_t xi, uint32_t t, uint32_t s, uint32_t& pr, uint32_t& pi) {
  const uint32_t a = hfma(xi, t, xr);
  pi = hfma(a, s, xi);
  pr = hfma(pi, t, a);
}
template <int BH> __device__ __forceinline__ void fft_e1(const uint32_t (&d)[32], const uint32_t (&tw)[12], uint32_t (&a2)[2][2][4]) {
#pragma unroll
  for (int be = 0; be < 2; be++)
#pragma unroll
    for (int s = 0; s < 2; s++) {
      const int o = 16 * s + 8 * be + 2 * BH, p = 4 * BH;
      uint32_t pr, pi;
      rot(d[o], d[o + 1], tw[p], tw[p + 1], pr, pi);
      const uint32_t qr = hfnma(d[o + 5], tw[p + 2], d[o + 4]), qi = hfma(d[o + 4], tw[p + 2], d[o + 5]);
      a2[be][0][s] = hfma(qi, tw[p + 3], pr);
      a2[be][0][2 + s] = hfnma(qr, tw[p + 3], pi);
      a2[be][1][s] = hfnma(qi, tw[p + 3], pr);
      a2[be][1][2 + s] = hfma(qr, tw[p + 3], pi);
    }
}
__device__ __forceinline__ uint32_t hfms(uint32_t a, uint32_t b, uint32_t c) {
  uint32_t r;
  asm("{\n.reg .b32 t;\nneg.f16x2 t, %3;\nfma.rn.f16x2 %0, %1, %2, t;\n}\n" : "=r"(r) : "r"(a), "r"(b), "r"(c));
  return r;
}
__device__ __forceinline__ void fft_e2(const uint32_t (&d0)[8], const uint32_t (&d1)[8], uint32_t (&a3)[2][4]) {
#pragma unroll
  for (int j = 0; j < 2; j++) {
    const uint32_t ur = d0[2 * j], ui = d0[4 + 2 * j], hr = d0[2 * j + 1], hi = d0[5 + 2 * j];
    const uint32_t vr = d1[2 * j], vi = d1[4 + 2 * j], gr = d1[2 * j + 1], gi = d1[5 + 2 * j];
    const uint32_t pr = hfnma(ui, hi, hmul(ur, hr)), pi = hfma(ui, hr, hmul(ur, hi));
    a3[j][0] = pr;
    a3[j][2] = pi;
    a3[j][1] = hfnma(vi, hi, hfma(vr, hr, hfnma(ui, gi, hfms(ur, gr, pi))));
    a3[j][3] = hfma(vi, hr, hfma(vr, hi, hfma(ui, gr, hfma(ur, gi, pr))));
  }
}
__device__ __forceinline__ void fft_e3(const uint32_t (&d)[2][8], const uint32_t (&tw)[12], uint32_t zaddr) {
#pragma unroll
  for (int c = 0; c < 2; c++) {
    uint32_t zr[4], zi[4];
#pragma unroll
    for (int nb = 0; nb < 4; nb++) {
      const int i = 4 * (nb & 1) + (nb >> 1);
      rot(d[c][i], d[c][i + 2], tw[8 + 2 * (nb & 1)], tw[9 + 2 * (nb & 1)], zr[nb], zi[nb]);
    }
    stsm4(zaddr + c * 2048, zr[0], zr[1], zr[2], zr[3]);
    stsm4(zaddr + c * 2048 + 1024, zi[0], zi[1], zi[2], zi[3]);
  }
}
__device__ __forceinline__ float bf_lo(uint32_t v) {
  uint32_t r;
  asm("prmt.b32 %0, %1, 0, 0x1044;\n" : "=r"(r) : "r"(v));
  return __uint_as_float(r);
}
__device__ __forceinline__ float bf_hi(uint32_t v) { return __uint_as_float(v & 0xffff0000u); }
__device__ __forceinline__ float ex2(float x) {
  float r;
  asm("ex2.approx.ftz.f32 %0, %1;\n" : "=f"(r) : "f"(x));
  return r;
}
__device__ __forceinline__ float rcp(float x) {
  float r;
  asm("rcp.approx.ftz.f32 %0, %1;\n" : "=f"(r) : "f"(x));
  return r;
}

__device__ __forceinline__ int g2_a(int s, int h) { return (((0xA1023 ^ (h * 0x11)) >> (4 * s)) & 15) * 16384; }
__device__ __forceinline__ int g2_b(int s) { return (((11 | 13 << 5 | 22 << 10 | 26 << 15 | 24 << 20) >> (5 * s)) & 31) * 8192; }
static_assert(OFF_U == 10 * 16384 && OFF_H == 12 * 16384 && OFF_OP == 2 * 16384 && OFF_Q + 6 * 4096 == 11 * 8192, "units");
__device__ __forceinline__ int g2_k(int hp, int i) {
  return i < 2 ? hp ^ 1 ^ i : i < 4 ? (hp & ~1) ^ i : ((hp & ~3) + i) & 15; }
__device__ __forceinline__ int y_slot(int wg, int it) {
  static_assert(T_B2 == T_TW + 8192 && T_A1 == T_B2 + 4096, "y slots");
  return OFF_T + T_TW + ((it + 3) & 3) * 4096 + wg * 2048;
}

__device__ __forceinline__ void to_arr(uint32_t (&d)[4], uint4 v) { d[0] = v.x; d[1] = v.y; d[2] = v.z; d[3] = v.w; }

__device__ __forceinline__ void attn_stage(uint32_t sb, int blk, int lane, const float (&acc)[96], uint32_t (&k1)[2][4]) {
  const int lr = lane & 7, lm = lane >> 3;
  const uint32_t base = sb + OFF_VP + (blk * 16 + lr + 8 * (lm & 1)) * 128;
#pragma unroll
  for (int i = 0; i < 8; i++) k1[i >> 2][i & 3] = pack_bf16(acc[34 + 4 * i], acc[35 + 4 * i]);
  const uint32_t kh = sb + OFF_OP + ((blk + 1) & 15) * 2048 + lane * 16;
  sts128(kh, k1[0][0], k1[0][1], k1[0][2], k1[0][3]);
  sts128(kh + 512, k1[1][0], k1[1][1], k1[1][2], k1[1][3]);
#pragma unroll
  for (int j = 0; j < 8; j += 2)
    stsm4(base + (((j + (lm >> 1)) ^ lr) << 4), pack_bf16(acc[64 + 4 * j], acc[65 + 4 * j]),
          pack_bf16(acc[66 + 4 * j], acc[67 + 4 * j]), pack_bf16(acc[68 + 4 * j], acc[69 + 4 * j]),
          pack_bf16(acc[70 + 4 * j], acc[71 + 4 * j]));
}
__device__ __forceinline__ void attn_pack(const float (&acc)[96], uint32_t (&qa)[2][8], uint32_t (&k0)[2][4]) {
#pragma unroll
  for (int hd = 0; hd < 2; hd++) {
#pragma unroll
    for (int i = 0; i < 8; i++) {
      asm volatile("cvt.rn.bf16x2.f32 %0, %1, %2;\n" : "=r"(qa[hd][i]) : "f"(acc[16 * hd + 2 * i + 1]), "f"(acc[16 * hd + 2 * i]));
    }
#pragma unroll
    for (int i = 0; i < 4; i++) {
      asm volatile("cvt.rn.bf16x2.f32 %0, %1, %2;\n" : "=r"(k0[hd][i]) : "f"(acc[33 + 16 * hd + 4 * i]), "f"(acc[32 + 16 * hd + 4 * i]));
    }
  }
}
__device__ __forceinline__ void attn_own(const uint32_t (&k0)[2][4], const uint32_t (&k1)[2][4], bool le0, bool le1,
                                         const uint32_t (&qa)[2][8], float (&l)[2][4]) {
#pragma unroll
  for (int hd = 0; hd < 2; hd++) {
    float s0[4], s1[4];
    mma16816_z(s0, qa[hd][0], qa[hd][1], qa[hd][2], qa[hd][3], k0[hd][0], k0[hd][1]);
    mma16816_z(s1, qa[hd][0], qa[hd][1], qa[hd][2], qa[hd][3], k1[hd][0], k1[hd][1]);
    mma16816(s0, qa[hd][4], qa[hd][5], qa[hd][6], qa[hd][7], k0[hd][2], k0[hd][3]);
    mma16816(s1, qa[hd][4], qa[hd][5], qa[hd][6], qa[hd][7], k1[hd][2], k1[hd][3]);
    l[hd][0] = s0[0];
    l[hd][1] = s0[1];
    l[hd][2] = le0 ? s1[2] : s0[2];
    l[hd][3] = le1 ? s1[3] : s0[3];
  }
}
template <int N> __device__ __forceinline__ void quad_softmax(float (&x)[N][2], uint32_t (&pp)[N]) {
  const float c2 = 1.4426950408889634f;
  uint32_t q[N], mx[N / 2];
#pragma unroll
  for (int n = 0; n < N; n++) {
    const uint32_t r = pack_bf16(x[n][0], x[n][1]);
    q[n] = bfma2(r, 0x3e353e35u, bmul2(r, 0x379e379eu));
    x[n][0] = bf_lo(q[n]);
    x[n][1] = bf_hi(q[n]);
  }
#pragma unroll
  for (int n = 0; n < N / 2; n++)
    mx[n] = bmax2(__byte_perm(q[2 * n], q[2 * n + 1], 0x5410), __byte_perm(q[2 * n], q[2 * n + 1], 0x7632));
#pragma unroll
  for (int o = 1; o <= 2; o++)
#pragma unroll
    for (int n = 0; n < N / 2; n++) mx[n] = bmax2(mx[n], __shfl_xor_sync(0xffffffffu, mx[n], o));
  float m[N], t[N];
#pragma unroll
  for (int n = 0; n < N / 2; n++) {
    m[2 * n] = bf_lo(mx[n]);
    m[2 * n + 1] = bf_hi(mx[n]);
  }
#pragma unroll
  for (int n = 0; n < N; n++) {
    const float nm = -m[n] * c2;
    x[n][0] = ex2(fmaf(x[n][0], c2, nm));
    x[n][1] = ex2(fmaf(x[n][1], c2, nm));
    t[n] = x[n][0] + x[n][1];
  }
#pragma unroll
  for (int o = 1; o <= 2; o++)
#pragma unroll
    for (int n = 0; n < N; n++) t[n] += __shfl_xor_sync(0xffffffffu, t[n], o);
#pragma unroll
  for (int n = 0; n < N; n++) {
    const float inv = rcp(t[n]);
    pp[n] = pack_bf16(x[n][0] * inv, x[n][1] * inv);
  }
}
__device__ __forceinline__ void attn_pv(uint32_t dst, const uint32_t (&va)[4], const uint32_t (&vb)[4], uint32_t pp,
                                        uint32_t maskLE) {
  const uint32_t b0 = pp & ~maskLE, b1 = pp & maskLE;
  float oa[4], ob[4];
  mma16816_z(oa, va[0], va[1], va[2], va[3], b0, b1);
  mma16816_z(ob, vb[0], vb[1], vb[2], vb[3], b0, b1);
  stsm4t(dst, pack_bf16(oa[0], oa[1]), pack_bf16(oa[2], oa[3]), pack_bf16(ob[0], ob[1]), pack_bf16(ob[2], ob[3]));
}

template <int MODE>
__global__ void __cluster_dims__(2, 1, 1) __launch_bounds__(NTHREADS, 1)
fused_kernel(const Params p, const __grid_constant__ CUtensorMap tmX, const __grid_constant__ CUtensorMap tmW,
             const __grid_constant__ CUtensorMap tmWo,
             const __grid_constant__ CUtensorMap tmQ,
             const __grid_constant__ CUtensorMap tmXh, const __grid_constant__ CUtensorMap tmWh) {
  extern __shared__ __align__(1024) uint8_t smem[];
  const uint32_t sb = smem_u32(smem) + HALO;
  const uint32_t bars = sb + OFF_BAR;
  const int tid = threadIdx.x, lane = tid & 31, warp = __shfl_sync(0xffffffffu, tid >> 5, 0);
  const int rank = blockIdx.x & 1;
  const bool halo_cta = blockIdx.x < 4;
  if (halo_cta && MODE != 0) return;
  int grp, mem;
  {
    const int t = (blockIdx.x >> 1) - 4, u = t - 32;
    const int q7 = (u * 37) >> 8;
    const bool lo = (unsigned)t < 32u, mid = (unsigned)u < 28u;
    grp = lo ? (t & 7) : (mid ? 1 + u - 7 * q7 : 0);
    mem = lo ? (t >> 3) : (mid ? 4 + q7 : (t < 0 ? t + 6 : t - 54));
  }
  const int rg = (grp >> 2) * 4 + (mem >> 1), hp = (grp & 3) * 4 + (mem & 1) * 2 + rank;
  const int rb2 = (grp >> 2) * 8 + mem, cb2 = (grp & 3) * 2 + rank;
  const int chb = grp * 16 + mem * 2 + rank;
  const int cta = rg * 16 + hp;
  const int par = rg >> 2, gidx = rg & 3;

  if (tid < 256 && !halo_cta && MODE != 2) {
    const int r = tid >> 3, c = tid & 7;
    const uint32_t so = r * 128 + ((c ^ (r & 7)) << 4);
    const __nv_bfloat16* wg0 = p.w + (size_t)r * (3 * DM) + hp * 64 + c * 8;
    const __nv_bfloat16* xg0 = p.x + (size_t)(2 * (gidx * 256 + r) + par) * DM + c * 8;
#pragma unroll
    for (int j = 0; j < 3; j++) cp_async16n(sb + OFF_1B + j * 4096 + so, wg0 + j * DM);
#pragma unroll
    for (int i = 0; i < 8; i++) cp_async16n(sb + i * 4096 + so, xg0 + (size_t)i * 64 * DM);
    asm volatile("cp.async.commit_group;\n" ::: "memory");
  }
  if (tid == 256) {
    prefetch_tmap(halo_cta ? &tmXh : &tmX);
#pragma unroll
    for (int i = 0; i < NS1B; i++) mbar_init(bars + 8 * (BAR_FULLB + i), 1);
#pragma unroll
    for (int i = 0; i < NS1A; i++) mbar_init(bars + 8 * (BAR_FULLA + i), 1);
    asm volatile("fence.mbarrier_init.release.cluster;\n" ::: "memory");
    if (!halo_cta && MODE != 2) {
      mbar_expect_tx(bars + 8 * (BAR_FULLB + 1), STG1B);
      tma_load_3d(sb + OFF_1B + 1 * STG1B, &tmW, bars + 8 * (BAR_FULLB + 1), hp * 64, 32, 0);
      mbar_expect_tx(bars + 8 * (BAR_FULLB + 2), STG1B);
      tma_load_3d(sb + OFF_1B + 2 * STG1B, &tmW, bars + 8 * (BAR_FULLB + 2), hp * 64, 64, 0);
    } else {
      prefetch_tmap(&tmWh);
    }
  } else if (tid == 288) {
#pragma unroll
    for (int i = 0; i < NS1A; i++) mbar_init(bars + 8 * (BAR_EMPTYA + i), 4);
#pragma unroll
    for (int i = 0; i < NS1B; i++) mbar_init(bars + 8 * (BAR_EMPTYB + i), 2);
    asm volatile("fence.mbarrier_init.release.cluster;\n" ::: "memory");
  } else if (tid == 320) {
#pragma unroll
    for (int i = 0; i < NS2; i++) {
      mbar_init(bars + 8 * (BAR_FULL2 + i), 1);
      mbar_init(bars + 8 * (BAR_EMPTY2 + i), 4);
    }
    mbar_init(bars + 8 * BAR_DEAD, 2);
    mbar_init(bars + 8 * (BAR_DEAD + 1), 2);
    mbar_init(bars + 8 * BAR_X, 2);
    mbar_init(bars + 8 * BAR_REL, 2);
    asm volatile("fence.mbarrier_init.release.cluster;\n" ::: "memory");
  } else if (tid == 352) {
    mbar_init(bars + 8 * BAR_T, 1);
    mbar_init(bars + 8 * BAR_UH, 3);
    mbar_init(bars + 8 * BAR_LFREE, 4);
    mbar_init(bars + 8 * BAR_LAND, 1);
    mbar_init(bars + 8 * BAR_U, 1);
    mbar_init(bars + 8 * BAR_Q, 1);
    mbar_init(bars + 8 * BAR_STG, 9);
    asm volatile("fence.mbarrier_init.release.cluster;\n" ::: "memory");
  }
  if (warp == 8) PROF2(23);
  cluster_sync_all();
  if (warp == 8) PROF2(24);

  if (warp >= 8) {
    const int hw = warp - 8;
    const int lr = lane & 7, lm = lane >> 3;
    auto g1_issue_a = [&](int j, int s) {
      const uint32_t fb = bars + 8 * (BAR_FULLA + s);
      mbar_expect_tx(fb, STG1A);
      tma_load_3d_mc(sb + s * STG1A + rank * 16384, &tmX, fb, j * 64, par, gidx * 256 + rank * 128);
    };
    auto g1_issue_b = [&](int kb, int s) {
      const uint32_t fb = bars + 8 * (BAR_FULLB + s);
      mbar_expect_tx(fb, STG1B);
      tma_load_3d(sb + OFF_1B + s * STG1B, &tmW, fb, hp * 64, kb * 32, 0);
    };
    asm volatile("setmaxnreg.dec.sync.aligned.u32 %0;\n" :: "n"(REG_HELP));

    if (halo_cta) {
      if (hw == 0) {
        int s = 0, ph = 1;
#pragma unroll 1
        for (int kb = 0; kb < 16; kb++) {
          mbar_wait(bars + 8 * (BAR_EMPTYB + s), ph);
          const uint32_t fb = bars + 8 * (BAR_FULLB + s), st = sb + s * STGH;
          if (elect_one()) {
            mbar_expect_tx(fb, STGH);
            tma_load_4d(st, &tmXh, fb, kb * 64, 248, 0, 0);
            tma_load_3d(st + 8192, &tmWh, fb, 0, kb * 64, 16 + blockIdx.x * 4);
            tma_load_3d(st + 8192 + 32768, &tmWh, fb, 0, kb * 64, 32 + blockIdx.x * 4);
          }
          if (++s == 3) { s = 0; ph ^= 1; }
        }
      }
      __syncwarp();
    } else if (hw == 0) {
      uint32_t epoch = 0;
      if (lane < (MODE == 2 ? NS2 : 2)) mbar_arrive_cluster_n(mapa(bars, rank) + 8 * (BAR_EMPTY2 + lane), 4);
      if (MODE != 2) {
      epoch = ld_relaxed(g_flag_o + 2 * cta) + 1;
      if (lane == 0) {
        mbar_expect_tx(bars + 8 * BAR_U, 32768);
        mbar_expect_tx(bars + 8 * BAR_LAND, 32768 + 64);
        mbar_expect_tx(bars + 8 * BAR_Q, 32768);
        mbar_expect_tx(bars + 8 * BAR_T, T_END);
      }
      {
        int sa = 1, pha = 1, sbb = 2, phb = 1;
#pragma unroll 1
        for (int kb = 2; kb < 32; kb++) {
          if (!(kb & 1)) {
            mbar_wait(bars + 8 * (BAR_EMPTYA + sa), pha);
            if (elect_one()) g1_issue_a(kb >> 1, sa);
            if (++sa == NS1A) { sa = 0; pha ^= 1; }
          }
          mbar_wait(bars + 8 * (BAR_EMPTYB + sbb), phb);
          if (kb > 2 && elect_one()) g1_issue_b(kb, sbb);
          __syncwarp();
          if (kb >= PF0 && kb < PF0 + 12)
            prefetch_l2((kb < PF0 + 8 ? p.q + (size_t)chb * 16384 + (kb - PF0) * 2048 : p.wo + (size_t)chb * 8192 + (kb - PF0 - 8) * 2048) + lane * 64);
          if (kb == 4) PROF2(27);
          if (kb == 1) PROF2(38);
          if (kb == 2) PROF2(39);
          if (++sbb == NS1B) { sbb = 0; phb ^= 1; }
        }
      }
      static_assert(32 % NS1B == 2 && (32 / NS1B) % 2 == 0 && OFF_Q + STG2 + 6 * 4096 == OFF_1B + 2 * STG1B, "slots / parity of these loads");
      const uint8_t* tab = reinterpret_cast<const uint8_t*>(g_tab);
      if (lane == 0) {
        prefetch_tmap(&tmWo);
        prefetch_tmap(&tmQ);
        bulk_load(sb + OFF_T + T_A1, tab + T_A1, T_END - T_A1, bars + 8 * BAR_T);
        mbar_wait(bars + 8 * (BAR_EMPTYB + 2), 1);
        tma_load_5d(sb + OFF_Q + STG2 + 6 * 4096, &tmQ, bars + 8 * BAR_Q, (chb & ~1) * 8, rank * 32 + 24);
        tma_load_5d(sb + OFF_Q + STG2 + 7 * 4096, &tmQ, bars + 8 * BAR_Q, (chb & ~1) * 8, rank * 32 + 28);
        if (gidx != 0) wait_flag(g_flag_h + (hp >> 2), epoch);
      }
      __syncwarp();
      {
        uint4 hk0 = make_uint4(0, 0, 0, 0), hk1 = hk0, hv0 = hk0, hv1 = hk0;
        if (gidx != 0) {
          const uint4* src = g_halo + cta * 128 + lane;
          hk0 = __ldcg(src); hk1 = __ldcg(src + 32); hv0 = __ldcg(src + 64); hv1 = __ldcg(src + 96);
        }
        if (lane == 0) {
          mbar_wait(bars + 8 * (BAR_EMPTYB + 3), 1);
          bulk_load(sb + OFF_T, tab, T_TW, bars + 8 * BAR_T);
        }
        __syncwarp();
        PROF2(18);
        sts128(sb - HALO + lane * 16, hk0.x, hk0.y, hk0.z, hk0.w);
        sts128(sb - HALO + 512 + lane * 16, hk1.x, hk1.y, hk1.z, hk1.w);
        stsm4(sb - HALO + 1024 + lr * 128 + ((lm ^ lr) << 4), hv0.x, hv0.y, hv0.z, hv0.w);
        stsm4(sb - HALO + 1024 + lr * 128 + (((4 + lm) ^ lr) << 4), hv1.x, hv1.y, hv1.z, hv1.w);
        __syncwarp();
        if (lane == 0) {
          mbar_arrive(bars + 8 * BAR_STG);
          mbar_wait(bars + 8 * (BAR_EMPTYB + 4), 1);
          bulk_load(sb + OFF_T + T_TW, tab + T_TW, T_A1 - T_TW, bars + 8 * BAR_T);
#pragma unroll 1
          for (int i = 0; i < 6; i++) tma_load_5d(sb + OFF_Q + i * 4096, &tmQ, bars + 8 * BAR_Q, (chb & ~1) * 8, rank * 32 + i * 4);
          if (MODE == 0) {
            mbar_wait(bars + 8 * BAR_EMPTYB, 0);
            tma_load_3d(sb + g2_b(0), &tmWo, bars + 8 * BAR_FULL2, 0, g2_k(hp, 0) * 64, cb2 * 2);
            tma_load_3d(sb + g2_b(1), &tmWo, bars + 8 * (BAR_FULL2 + 1), 0, g2_k(hp, 1) * 64, cb2 * 2);
          }
        }
        __syncwarp();
      }
      }
      if (MODE != 1) {
        auto korder = [&](int i) { return MODE == 2 ? i : g2_k(hp, i); };
        const __nv_bfloat16* osrc = g_o + (size_t)(rb2 >> 1) * 16 * 16384 + ((rb2 & 1) * 2 + rank) * 4096;
        const uint32_t* flag = g_flag_o + ((rb2 >> 1) * 32 + korder(lane & 15) * 2 + (rb2 & 1));
        uint32_t ready = MODE == 0 ? 0u : ~0u, pv = 0;
        const __nv_bfloat16* o23[2] = {osrc + korder(2) * 16384, osrc + korder(3) * 16384};
        if (MODE == 0) {
          asm volatile("" : "+l"(o23[0]), "+l"(o23[1]), "+l"(flag));
          if (lane < 4 && lane != 1) mbar_expect_tx(bars + 8 * (BAR_FULL2 + lane), STG2);
          mbar_wait_idle(bars + 8 * (BAR_EMPTY2 + 2), 0);
          mbar_wait(bars + 8 * (BAR_EMPTY2 + 3), 0);
          mbar_wait_idle(bars + 8 * BAR_REL, 0);
          { const uint32_t t0 = clock(); while ((uint32_t)clock() - t0 < PDELAY) __nanosleep(20); }
        }
#pragma unroll
        for (int i = MODE == 0 ? 2 : 0; i < 16; i++) {
          const int kb = korder(i), s = i % NS2, ph = (i / NS2) & 1;
          const uint32_t fb = bars + 8 * (BAR_FULL2 + s);
          if (!((ready >> i) & 1)) {
            int n = 0;
            do {
              ready |= __ballot_sync(0xffffffffu, ld_acquire(flag) == epoch);
            } while (!((ready >> i) & 1) && ++n < SPIN_LIMIT);
            fence_async_all();
          }
          if (i == 2) PROF(21);
          const bool pre = MODE == 0 && i < 4;
          if (!pre) mbar_wait(bars + 8 * (BAR_EMPTY2 + s), ph);
          if (elect_one()) {
            if (!pre) mbar_expect_tx(fb, STG2);
            asm volatile(
                "cp.async.bulk.shared::cluster.global.mbarrier::complete_tx::bytes.multicast::cluster [%0], [%1], %2, [%3], %4;\n"
                ::"r"(sb + g2_a(s, rb2 & 1) + rank * 8192), "l"(pre ? o23[i & 1] : osrc + kb * 16384), "r"(8192), "r"(fb), "h"((uint16_t)3) : "memory");
            if (!pre) tma_load_3d(sb + g2_b(s), &tmWo, fb, 0, kb * 64, cb2 * 2);
          }
          if (MODE == 0 && i == 3) pv = ld_relaxed(flag);
          if (MODE == 0 && i == 4) {
            ready |= __ballot_sync(0xffffffffu, pv == epoch);
            asm volatile("fence.acquire.gpu;\n" ::: "memory");
            fence_async_all();
          }
          if (i == 3) PROF(37);

        }
      }
      __syncwarp();
    } else if (MODE != 2) {
      {
        const int g = lane >> 2, t = lane & 3;
        uint32_t w[2][4];
#pragma unroll
        for (int h = 0; h < 2; h++) {
          const uint2 x = __ldg(reinterpret_cast<const uint2*>(p.shift_k + ((chb & ~1) * 8 + h * 8 + g) * 4));
          w[h][0] = __byte_perm(x.x, x.x, 0x1010);
          w[h][1] = __byte_perm(x.x, x.x, 0x3232);
          w[h][2] = __byte_perm(x.y, x.y, 0x1010);
          w[h][3] = __byte_perm(x.y, x.y, 0x3232);
        }
        auto swz = [](int r) { return (((r & 29) | ((r ^ (r >> 2)) & 2)) << 5) | (r & 16); };
        const uint32_t kring = sb + OFF_H + (hw - 1) * 8192, vring = kring + 4096;
        const int s0 = rank * 32 + (hw - 1) * 11, s1 = hw == 3 ? rank * 32 + 32 : s0 + 11;
        const size_t goff = (size_t)(lane >> 1) * DM + (chb & ~1) * 8 + (lane & 1) * 8;
        const __nv_bfloat16* kg = p.k + goff;
        const __nv_bfloat16* vg = p.v + goff;
        const uint32_t d0 = swz(lane >> 1) ^ ((lane & 1) << 4), d1 = swz(16 + (lane >> 1)) ^ ((lane & 1) << 4);
        auto issue = [&](int st) {
          const uint32_t so = (st & 3) << 10;
          cp_async16(kring + so + d0, kg + (size_t)st * 32 * DM, 16);
          cp_async16(kring + so + d1, kg + (size_t)(st * 32 + 16) * DM, 16);
          cp_async16(vring + so + d0, vg + (size_t)st * 32 * DM, 16);
          cp_async16(vring + so + d1, vg + (size_t)(st * 32 + 16) * DM, 16);
        };
        const int xa = 8 * (lr >> 1) + 2 * lm + (lr & 1), xb = 8 * (lr >> 1) - 4 + 2 * (lm & 1) + (lr & 1);
        const uint32_t la = swz(xa), lb = swz(xb & 31);
        const int backb = xb < 0 ? 1 : 0;
        const uint32_t ud[2] = {mapa(sb + OFF_U + g * 4096 + t * 16, 0), mapa(sb + OFF_U + g * 4096 + t * 16, 1)};
        const uint32_t ub[2] = {mapa(bars + 8 * BAR_U, 0), mapa(bars + 8 * BAR_U, 1)};
        if (lane == 0) mbar_wait(bars + 8 * (BAR_FULLB + NS1B - 1), 0);
        __syncwarp();
        if (lane >= 24) cp_async16(kring + (((s0 - 1) & 3) << 10) + d1, s0 > 0 ? kg + (size_t)(s0 * 32 - 16) * DM : kg, s0 > 0 ? 16 : 0);
        issue(s0);
        asm volatile("cp.async.commit_group;\n" ::: "memory");
        issue(s0 + 1);
        asm volatile("cp.async.commit_group;\n" ::: "memory");
#pragma unroll 1
        for (int st = s0; st < s1; st++) {
          if (st + 2 < s1) issue(st + 2);
          if (hw == 1 && st - s0 < 8) prefetch_l2(p.ssm_k + (size_t)(chb * 8 + st - s0) * SEQ + lane * 64);
          if (hw == 2 && st == s0 + 4 && lane < 2) prefetch_l2(g_tab + (chb * 2 + lane) * 32);
          const uint32_t uo = (st ^ ((g ^ (st >> 2)) & 1)) * 64;
          asm volatile("cp.async.commit_group;\n" ::: "memory");
          asm volatile("cp.async.wait_group 2;\n" ::: "memory");
          __syncwarp();
#pragma unroll
          for (int h = 0; h < 2; h++) {
            uint32_t e[6], vv[4], e4[4];
            ldsm4t(e4, kring + ((st & 3) << 10) + (la ^ (h << 4)));
            ldsm2t(e[0], e[1], kring + (((st - backb) & 3) << 10) + (lb ^ (h << 4)));
            ldsm4t(vv, vring + ((st & 3) << 10) + (la ^ (h << 4)));
            e[2] = e4[0]; e[3] = e4[1]; e[4] = e4[2]; e[5] = e4[3];
            uint32_t o[5];
#pragma unroll
            for (int i = 0; i < 5; i++) o[i] = __byte_perm(e[i], e[i + 1], 0x5432);
#pragma unroll
            for (int i = 0; i < 4; i++) {
              uint32_t a = bmul2(o[i], w[h][3]);
              a = bfma2(e[i + 1], w[h][2], a);
              a = bfma2(o[i + 1], w[h][1], a);
              a = bfma2(e[i + 2], w[h][0], a);
              vv[i] = bmul2(a, vv[i]);
            }
            st_async128(ud[h] + uo, ub[h], vv[0], vv[1], vv[2], vv[3]);
          }
          __syncwarp();
        }
        PROF(16);
      }
      {
        const int rw = (lane >> 3) + (lane & 4), ck = lane & 3;
        const uint32_t so = rw * 64 + ck * 16, dof = rw * 128 + ((ck ^ rw) << 4);
        const uint8_t* hsrc = reinterpret_cast<const uint8_t*>(p.ssm_k + (size_t)chb * 8 * SEQ) + so;
        const float dv = lane < 8 ? __bfloat162float(p.ssm_D[chb * 8 + lane]) : 0.f;
        uint32_t x[32];
        auto load = [&](const uint8_t* src, int i) {
          asm volatile("ld.v4.u32 {%0,%1,%2,%3}, [%4];\n" : "=r"(x[4 * i]), "=r"(x[4 * i + 1]), "=r"(x[4 * i + 2]), "=r"(x[4 * i + 3])
                       : "l"(src + i * 512) : "memory");
        };
#pragma unroll
        for (int i = 0; i < 8; i++) load(hsrc + (hw - 1) * 4096, i);
        nb_sync(NB_HELP3, 96);
        mbar_wait(bars + 8 * BAR_U, 0);
        int eh = 0;
#pragma unroll 1
        for (int n = 2 * (hw - 1); n < 16; n += (n & 1) ? 5 : 1) {
          const int c = n >> 1;
          const uint8_t* nsrc = (n & 1) ? hsrc + (c < 5 ? c + 3 : c) * 4096
                                        : smem + HALO + OFF_U + c * 4096 + (so ^ (((c ^ (lane >> 2)) & 1) << 6));
          const uint32_t dst = sb + ((n & 1) ? OFF_U : OFF_H) + c * 4096 + dof;
          const float dc = __shfl_sync(0xffffffffu, dv, c);
          const float h0 = bf_lo(x[0]) + ((lane | (n & 1)) == 0 ? dc : 0.f), h1 = bf_hi(x[0]);
          x[0] = pack_bf16(h0, h1);
          uint32_t m[2] = {x[0], x[1]};
#pragma unroll
          for (int i = 2; i < 32; i++) asm("max.xorsign.abs.bf16x2 %0, %0, %1;\n" : "+r"(m[i & 1]) : "r"(x[i]));
          asm("max.xorsign.abs.bf16x2 %0, %0, %1;\n" : "+r"(m[0]) : "r"(m[1]));
          const uint32_t e = max(__reduce_max_sync(0xffffffffu, max((m[0] >> 7) & 255u, (m[0] >> 23) & 255u)), 5u);
          const uint32_t sc = (259u - e) * 0x00800080u;
#pragma unroll
          for (int i = 0; i < 8; i++) {
            uint32_t o[4];
#pragma unroll
            for (int j = 0; j < 4; j++) {
              const uint32_t v = bmul2(x[4 * i + j], sc);
              asm("cvt.rn.f16x2.f32 %0, %1, %2;\n" : "=r"(o[j]) : "f"(bf_hi(v)), "f"(i + j == 0 ? h0 * bf_hi(sc) : bf_lo(v)));
            }
            sts128((dst + (i & 3) * 1024) ^ ((i >> 2) << 6), o[0], o[1], o[2], o[3]);
            load(nsrc, i);
          }
          if (n & 1) {
            const int f = min(max((int)e + eh - 129, 0), 254);
            if (lane < 2)
              asm volatile("st.async.weak.shared::cluster.mbarrier::complete_tx::bytes.b32 [%0], %2, [%1];\n"
                           ::"r"(mapa(sb + OFF_SC + rank * 32 + c * 4, lane)), "r"(mapa(bars + 8 * BAR_LAND, lane)), "r"(f << 7) : "memory");
          }
          eh = e;
        }
        fence_async_smem();
        __syncwarp();
        if (lane == 0) mbar_arrive(bars + 8 * BAR_UH);
        PROF(32);
      }
      if (hw < 3) {
        const uint32_t rb = mapa(bars, lane & 1);
        const uint32_t epoch = ld_relaxed(g_flag_o + (2 * cta + hw - 1)) + 1;
        const bool own = hw - 1 == (rb2 & 1);
        nb_sync(NB_OREADY + hw - 1, 160);
        if (lane == 0) {
          asm volatile("cp.async.bulk.global.shared::cta.bulk_group [%0], [%1], %2;\n" ::"l"(g_o + (size_t)cta * 16384 + (hw - 1) * 8192),
                       "r"(sb + OFF_OP + (hw - 1) * 16384), "r"(16384) : "memory");
          bulk_commit();
        }
        if (lane < 2) {
          mbar_arrive_cluster(rb + 8 * (BAR_EMPTY2 + 2));
          mbar_arrive_cluster(rb + 8 * (BAR_EMPTY2 + 3));
        }
        if (lane == 0) {
          bulk_wait0();
          if (own) mbar_expect_tx(bars + 8 * (BAR_FULL2 + 1), 16384);
          mbar_arrive_cluster(mapa(bars, own ? rank : rank ^ 1) + 8 * BAR_X);
          st_release(g_flag_o + (2 * cta + hw - 1), epoch);
          mbar_arrive(bars + 8 * BAR_REL);
        }
        __syncwarp();
        PROF(own ? 17 : 19);
      } else {
        if (MODE == 0) {
          mbar_wait_idle(bars + 8 * BAR_X, 0);
          if (elect_one())
            asm volatile("cp.async.bulk.shared::cluster.shared::cta.mbarrier::complete_tx::bytes [%0], [%1], %2, [%3];\n"
                         ::"r"(mapa(sb + g2_a(0, rb2 & 1), rank ^ 1)), "r"(sb + g2_a(1, rb2 & 1)), "r"(16384),
                         "r"(mapa(bars + 8 * BAR_FULL2, rank ^ 1)) : "memory");
        }
        if (MODE == 0) {
          mbar_wait_idle(bars + 8 * BAR_DEAD, 0);
          if (elect_one()) {
            tma_load_3d(sb + g2_b(2), &tmWo, bars + 8 * (BAR_FULL2 + 2), 0, g2_k(hp, 2) * 64, cb2 * 2);
            tma_load_3d(sb + g2_b(3), &tmWo, bars + 8 * (BAR_FULL2 + 3), 0, g2_k(hp, 3) * 64, cb2 * 2);
          }
        }
        __syncwarp();
      }
    }
    if (!halo_cta && MODE != 2) {
      {
        const int c8 = (4 * (lr >> 1) + 2 * (lm & 1) + (lr & 1)) & 7;
        const bool own = (lr >> 2) == rank;
        const uint32_t ya = sb + (own ? y_slot(c8 & 1, c8 >> 1) : OFF_LAND + c8 * 2048);
        const uint32_t yx = ((lm >> 1) ^ lr) << 4;
        const int row = (lane >> 4) * 8 + ((lane >> 3) & 1) * 16 + ((lane >> 2) & 1);
        uint2* og = reinterpret_cast<uint2*>(p.out + (size_t)(rank * 1024 + row) * (2 * DM) + (chb & ~1) * 8 + (lane & 3) * 4);
        const uint32_t qa = sb + OFF_Q + (lane >> 4) * 512 + (lane & 15) * 8;
        mbar_wait(bars + 8 * BAR_Q, 0);
        mbar_wait_idle(bars + 8 * BAR_LAND, 0);
        PROF(33);
        const uint32_t t0 = clock();
        const uint4 s4 = lds128(sb + OFF_SC + (lane & 3) * 16);
        const uint32_t sc[2] = {s4.x | (s4.y << 16), s4.z | (s4.w << 16)};
        auto fin = [&](uint32_t q2, uint32_t y2, uint32_t s2) {
          float lo, hi;
          asm("{\n.reg .b16 l, h;\nmov.b32 {l, h}, %2;\ncvt.f32.f16 %0, l;\ncvt.f32.f16 %1, h;\n}\n" : "=f"(lo), "=f"(hi) : "r"(y2));
          return bmul2(q2, bmul2(pack_bf16(lo, hi), s2));
        };
#pragma unroll 1
        for (int j = hw ? hw - 1 : 15; j < (hw ? 15 : 16); j += 3) {
          uint32_t y[4][4];
          uint2 q[8];
          while (hw && (uint32_t)clock() - t0 < j * PACE) __nanosleep(40);
          const uint32_t qj = qa + j * 2048 + (j >= 12 ? STG2 : 0);
#pragma unroll
          for (int i = 0; i < 4; i++) ldsm4t(y[i], ya + j * 128 + (yx ^ (i << 5)));
#pragma unroll
          for (int i = 0; i < 8; i++) q[i] = lds64(qj + (i >> 2) * 1024 + (i & 3) * 128);
#pragma unroll
          for (int i = 0; i < 8; i++) {
            og[(size_t)(j * 64 + (i >> 2) * 32 + (i & 3) * 2) * (2 * DM / 4)] =
                make_uint2(fin(q[i].x, y[i >> 1][2 * (i & 1)], sc[0]), fin(q[i].y, y[i >> 1][2 * (i & 1) + 1], sc[1]));
            if (i < 7) asm volatile("nanosleep.u32 40;\n" ::: "memory");
          }
        }
      }
      PROF(22);
    }
    cluster_sync_all();
  } else {
    asm volatile("setmaxnreg.inc.sync.aligned.u32 %0;\n" :: "n"(REG_MATH));
    if (warp == 0) PROF2(26);
    const int wg = warp >> 2;
    const int wtid = tid & 127;
    const bool signaller = (wtid == 0) || (wtid == 32);
    const uint32_t rbars = mapa(bars, wtid >> 5 & 1);

    if (halo_cta) {
      const uint32_t epoch = ld_relaxed(g_flag_h + blockIdx.x) + 1;
      float acc0[64], acc1[64];
      int s = 0, ph = 0;
#pragma unroll 1
      for (int kb = 0; kb < 16; kb++) {
        mbar_wait(bars + 8 * (BAR_FULLB + s), ph);
        const uint32_t st = sb + s * STGH;
        const uint64_t da = mkdesc(st, 16, 1024, 1);
        const uint64_t db = mkdesc(st + 8192 + wg * 32768, 8192, 1024, 1);
        wg_fence();
#pragma unroll
        for (int kk = 0; kk < 4; kk++) {
          wgmma_n128(acc0, da + 2 * kk, db + 128 * kk, kb + kk);
          wgmma_n128(acc1, da + 2 * kk, db + 1024 + 128 * kk, kb + kk);
        }
        wg_commit();
        wg_wait<0>();
        if (wtid == 0) mbar_arrive(bars + 8 * (BAR_EMPTYB + s));
        if (++s == 3) { s = 0; ph ^= 1; }
      }
      fence_regs(acc0);
      fence_regs(acc1);
      if ((warp & 3) != 3) {
#pragma unroll
        for (int hh = 0; hh < 2; hh++) {
          uint4* dst = g_halo + ((hh * 4 + (warp & 3) + 1) * 16 + blockIdx.x * 4) * 128 + wg * 64 + lane;
#pragma unroll
          for (int j = 0; j < 4; j++) {
            const int o = 16 * j + 2 * hh;
            dst[(j >> 1) * 128 + (j & 1) * 32] =
                make_uint4(pack_bf16(acc0[o], acc0[o + 1]), pack_bf16(acc0[o + 4], acc0[o + 5]),
                           pack_bf16(acc0[o + 8], acc0[o + 9]), pack_bf16(acc0[o + 12], acc0[o + 13]));
            dst[(2 + (j >> 1)) * 128 + (j & 1) * 32] =
                make_uint4(pack_bf16(acc1[o], acc1[o + 1]), pack_bf16(acc1[o + 4], acc1[o + 5]),
                           pack_bf16(acc1[o + 8], acc1[o + 9]), pack_bf16(acc1[o + 12], acc1[o + 13]));
          }
        }
      }
      nb_sync(NB_G1DONE, 256);
      if (tid == 0) st_release(g_flag_h + blockIdx.x, epoch);
      PROF(36);
      cluster_sync_all();
      return;
    }

    float acc[64];
    auto g2_step = [&](int s, int kb) {
      const uint64_t da = mkdesc(sb + g2_a(s, rb2 & 1) + wg * 8192, 16, 1024, 1);
      const uint64_t db = mkdesc(sb + g2_b(s), 8192, 1024, 1);
      wg_fence();
      wgmma_n128(acc, da, db, kb);
      wgmma_n128(acc, da + 2, db + 128, 1);
      wgmma_n128(acc, da + 4, db + 256, 1);
      wgmma_n128(acc, da + 6, db + 384, 1);
      wg_commit();
    };

    if (MODE != 2) {
    uint32_t a1[2][4], tw[12], d1[32];
    const uint32_t tb = sb + OFF_T + wtid * 16;
    const uint64_t dx = mkdesc(sb + OFF_U + wg * 4096, OFF_H - OFF_U, 1024, 1);
    auto s1 = [&](int it) {
      hmma_n128t<0>(d1, a1[0], dx + it * 512);
      hmma_n128t<1>(d1, a1[1], dx + it * 512 + 128);
      wg_commit();
    };
    auto ldtw = [&](int i) {
      const uint4 v = lds128(tb + T_TW + i * 2048);
      tw[4 * i] = v.x; tw[4 * i + 1] = v.y; tw[4 * i + 2] = v.z; tw[4 * i + 3] = v.w;
    };
    {
      float acc0[96], acc1[96];
      int sa = 0, pha = 0, sbb = 0, phb = 0;
      asm volatile("cp.async.wait_group 0;\n" ::: "memory");
      fence_async_smem();
      nb_sync(NB_FIRST, 256);
      if (tid == 0) {
        mbar_arrive(bars + 8 * BAR_FULLA);
        mbar_arrive(bars + 8 * BAR_FULLB);
      }
      PROF(0 + wg);
#pragma unroll 1
      for (int kb = 0; kb < 30; kb++) {
        if (!(kb & 1)) mbar_wait(bars + 8 * (BAR_FULLA + sa), pha);
        mbar_wait(bars + 8 * (BAR_FULLB + sbb), phb);
        if (kb == 0) PROF2(0 + wg);
        if (kb == 4 && wg == 0) PROF2(28);
        if (kb == 8 && wg == 0) PROF2(29);
        if (kb == 16 && wg == 0) PROF2(30);
        const uint64_t da = mkdesc(sb + sa * STG1A + wg * 16384 + (kb & 1) * 64, 16, 1024, 1);
        const uint64_t db = mkdesc(sb + OFF_1B + sbb * STG1B, 4096, 1024, 1);
        wg_fence();
        wgmma_n192(acc0, da, db, kb);
        wgmma_n192(acc1, da + 512, db, kb);
        wgmma_n192(acc0, da + 2, db + 128, 1);
        wgmma_n192(acc1, da + 514, db + 128, 1);
        wg_commit();
        wg_wait<1>();
        if (kb > 0) {
          if (wtid == 64) mbar_arrive(bars + 8 * (BAR_EMPTYB + (sbb == 0 ? NS1B - 1 : sbb - 1)));
          if (!(kb & 1) && signaller) mbar_arrive_cluster(rbars + 8 * (BAR_EMPTYA + (sa == 0 ? NS1A - 1 : sa - 1)));
        }
        if (++sbb == NS1B) { sbb = 0; phb ^= 1; }
        if ((kb & 1) && ++sa == NS1A) { sa = 0; pha ^= 1; }
      }
      const int blk0 = wg * 8 + (warp & 3);
      const int lr = lane & 7, lm = lane >> 3;
      const bool le0 = 2 * (lane & 3) <= (lane >> 2), le1 = 2 * (lane & 3) + 1 <= (lane >> 2);
      const uint32_t maskLE = (le0 ? 0x0000FFFFu : 0u) | (le1 ? 0xFFFF0000u : 0u);
      uint32_t k0[2][2][4], k1[2][2][4], qa[2][2][8];
      float l[2][2][4];
      {
        static_assert(15 % NS1A == 0 && 30 % NS1B == 0, "slots of the last k blocks");
        mbar_wait(bars + 8 * BAR_FULLA, 1);
        mbar_wait(bars + 8 * BAR_FULLB, 0);
        mbar_wait(bars + 8 * (BAR_FULLB + 1), 0);
        mbar_wait(bars + 8 * (BAR_EMPTYB + 2), 1);
        const uint64_t da = mkdesc(sb + wg * 16384, 16, 1024, 1);
        const uint64_t db = mkdesc(sb + OFF_1B, 4096, 1024, 1);
        wg_fence();
#pragma unroll
        for (int i = 0; i < 4; i++) wgmma_n192(acc0, da + 2 * i, db + (i >> 1) * (STG1B >> 4) + (i & 1) * 128, 1);
        wg_commit();
        wg_wait<1>();
        if (wtid == 64) mbar_arrive(bars + 8 * (BAR_EMPTYB + NS1B - 1));
#pragma unroll
        for (int i = 0; i < 2; i++) wgmma_n192(acc1, da + 512 + 2 * i, db + (i >> 1) * (STG1B >> 4) + (i & 1) * 128, 1);
        wg_commit();
        wg_wait<1>();
        fence_regs(acc0);
        attn_stage(sb, blk0, lane, acc0, k1[0]);
#pragma unroll
        for (int i = 2; i < 4; i++) wgmma_n192(acc1, da + 512 + 2 * i, db + (i >> 1) * (STG1B >> 4) + (i & 1) * 128, 1);
        wg_commit();
        attn_pack(acc0, qa[0], k0[0]);
        wg_wait<0>();
        fence_regs(acc1);
      }
      if (wtid == 64) mbar_arrive(bars + 8 * BAR_EMPTYB);
      PROF(2 + wg);
      attn_stage(sb, blk0 + 4, lane, acc1, k1[1]);
      __syncwarp();
      if (lane == 0) mbar_arrive(bars + 8 * BAR_STG);
      mbar_wait(bars + 8 * BAR_U, 0);
      attn_pack(acc1, qa[1], k0[1]);
      attn_own(k0[0], k1[0], le0, le1, qa[0], l[0]);
      attn_own(k0[1], k1[1], le0, le1, qa[1], l[1]);
      static_assert(OFF_VP == 0, "halo V rows");
      const uint32_t vl0 = sb + OFF_VP - 1024 + blk0 * 2048 + (lm >> 1) * 1024 + lr * 128 + (((lm & 1) ^ lr) << 4);
      const uint32_t vl[4] = {vl0, vl0 ^ 64, vl0 ^ 32, vl0 ^ 96};
      const uint32_t obase = sb + OFF_OP + (blk0 * 16 + lr) * 128 + ((lm ^ lr) << 4);
      mbar_wait(bars + 8 * BAR_STG, 0);
      {
        uint32_t km[4][4], va[8][4], vb[8][4], pp[8];
        float x[8][2];
#pragma unroll
        for (int n = 0; n < 4; n++) {
          const int blk = blk0 + 4 * (n >> 1);
          to_arr(km[n], lds128(sb + (blk == 0 ? -HALO : OFF_OP + blk * 2048) + (n & 1) * 512 + lane * 16));
        }
#pragma unroll
        for (int n = 0; n < 8; n++) {
          const uint32_t o = ((n >> 1) & 1) * 8192 + (n >> 2) * 1024;
          ldsm4t(va[n], vl[n & 1] + o);
          ldsm4t(vb[n], vl[2 + (n & 1)] + o);
        }
        const bool first = blk0 == 0 && gidx == 0;
#pragma unroll
        for (int n = 0; n < 4; n++) {
          const uint32_t(&q)[8] = qa[n >> 1][n & 1];
          float sm[4];
          mma16816_z(sm, q[0], q[1], q[2], q[3], km[n][0], km[n][1]);
          mma16816(sm, q[4], q[5], q[6], q[7], km[n][2], km[n][3]);
          if (n < 2 && first) sm[0] = sm[1] = -1e9f / 0.17677669529663687f;
          x[n][0] = le0 ? l[n >> 1][n & 1][0] : sm[0];
          x[n][1] = le1 ? l[n >> 1][n & 1][1] : sm[1];
          x[4 + n][0] = l[n >> 1][n & 1][2];
          x[4 + n][1] = l[n >> 1][n & 1][3];
        }
        quad_softmax<8>(x, pp);
#pragma unroll
        for (int n = 7; n >= 0; n--)
          attn_pv((obase ^ ((n & 1) << 6)) + ((n >> 1) & 1) * 8192 + (n >> 2) * 1024, va[n], vb[n], pp[n], maskLE);
      }
      fence_async_smem();
      nb_arrive(NB_OREADY + wg, 160);
    }

    {
      const int w = warp & 3;
      uint32_t a4[8][4];
      uint32_t d4[16];
      PROF(34 + wg);
      const uint64_t dz = mkdesc(sb + OFF_U + wg * 4096, 1024, 128, 0);
      const uint64_t db2 = mkdesc(sb + OFF_T + T_B2, 128, 512, 0), db3 = mkdesc(sb + OFF_T + T_B2, 1024, 128, 0);
      mbar_wait(bars + 8 * BAR_T, 0);
      mbar_wait(bars + 8 * BAR_UH, 0);
      to_arr(a1[0], lds128(tb + T_A1));
      to_arr(a1[1], lds128(tb + T_A1 + 2048));
      wg_fence();
      s1(0);
      ldtw(0);
      ldtw(1);
      const uint32_t za = sb + (w < 2 ? OFF_U : OFF_H) + wg * 4096 + (w & 1) * 8192 + lane * 16;
      const uint32_t yl = (wtid ^ (4 * rank + wg)) * 16;
      const uint32_t yown = mapa(sb, rank) + yl, yrem = mapa(sb + OFF_LAND + wg * 2048, rank ^ 1) + yl;
      const uint32_t yb[2] = {mapa(bars + 8 * BAR_LAND, 0), mapa(bars + 8 * BAR_LAND, 1)};
      wg_wait<0>();
      fence_regs(d1);
      auto s4 = [&]() {
        wg_fence();
#pragma unroll
        for (int ks = 0; ks < 8; ks++) {
          const uint64_t d = dz + (ks & 1) * 128 + ((ks >> 1) & 1) * 512 + (ks >> 2) * ((OFF_H - OFF_U) >> 4);
          if (ks == 0) hmma_n64t<0>(d4, a4[ks], d);
          else hmma_n64t<1>(d4, a4[ks], d);
        }
        wg_commit();
      };
      auto e4 = [&](int pr) {
        fence_regs(d4);
        mbar_wait(bars + 8 * (pr == 0 ? BAR_LFREE : BAR_DEAD + 1), 0);
#pragma unroll
        for (int u = 0; u < 2; u++) {
          const int it = 2 * pr + u;
          const uint32_t o = (yown + y_slot(wg, it)) ^ (pr << 5), m = (yrem + it * 4096) ^ (pr << 5);
          st_async128(rank ? m : o, yb[0], d4[8 * u], d4[8 * u + 1], d4[8 * u + 2], d4[8 * u + 3]);
          st_async128(rank ? o : m, yb[1], d4[8 * u + 4], d4[8 * u + 5], d4[8 * u + 6], d4[8 * u + 7]);
        }
      };
      uint32_t a2[2][2][2][4], a3[2][2][4], d2[2][2][8], d3[2][8];
      auto s2a = [&]() {
        wg_fence();
#pragma unroll
        for (int c = 0; c < 4; c++) hmma_n32<0, 0>(d2[c & 1][c >> 1], a2[0][c & 1][c >> 1], db2 + (c >> 1) * 128);
      };
      auto s2b = [&]() {
        wg_fence();
#pragma unroll
        for (int c = 0; c < 4; c++) {
          hmma_n32<1, 0>(d2[c & 1][c >> 1], a2[1][c & 1][c >> 1], db2 + (c >> 1) * 128 + 16);
          if (c & 1) wg_commit();
        }
      };
      fft_e1<0>(d1, tw, a2[0]);
      s2a();
      fft_e1<1>(d1, tw, a2[1]);
      s2b();
      s1(1);
      ldtw(2);
#pragma unroll
      for (int i = 0; i < 8; i++) to_arr(a4[i], lds128(tb + T_A4 + i * 2048));
#pragma unroll
      for (int it = 0; it < 4; it++) {
        if (it == 2) wg_wait<3>(); else if (it == 3) wg_wait<1>(); else wg_wait<2>();
        fence_regs(d2[0][0]);
        fence_regs(d2[1][0]);
        fft_e2(d2[0][0], d2[1][0], a3[0]);
        if (it == 2) wg_wait<2>(); else if (it == 3) wg_wait<0>(); else wg_wait<1>();
        fence_regs(d2[0][1]);
        fence_regs(d2[1][1]);
        fft_e2(d2[0][1], d2[1][1], a3[1]);
        wg_fence();
        hmma_n32<0, 1>(d3[0], a3[0][0], db3);
        hmma_n32<0, 1>(d3[1], a3[1][0], db3 + 128);
        hmma_n32<1, 1>(d3[0], a3[0][1], db3 + 32);
        hmma_n32<1, 1>(d3[1], a3[1][1], db3 + 160);
        wg_commit();
        if (it < 3) {
          wg_wait<1>();
          if (it == 2) {
            if (wtid == 64) mbar_arrive(bars + 8 * BAR_DEAD);
            e4(0);
          }
          fence_regs(d1);
          fft_e1<0>(d1, tw, a2[0]);
          s2a();
          wg_commit();
          wg_wait<1>();
        }
        if (it == 3) wg_wait<0>();
        if (it == 3 && wtid == 64) mbar_arrive(bars + 8 * (BAR_DEAD + 1));
        fence_regs(d3[0]);
        fence_regs(d3[1]);
        fft_e3(d3, tw, za + (it & 1) * 512);
        if (it < 3) {
          fft_e1<1>(d1, tw, a2[1]);
          s2b();
        }
        if (it & 1) {
          fence_async_smem();
          nb_sync(NB_WG + wg, 128);
          if (it == 1 && signaller) mbar_arrive_cluster(rbars + 8 * BAR_LFREE);
          s4();
        }
        if (it < 2) s1(it + 2);
        if (w == 0) PROF3(40 + 4 * wg + it);
      }
      if (MODE == 0) {
        mbar_wait(bars + 8 * BAR_FULL2, 0);
        g2_step(0, 0);
        wg_wait<1>();
      } else {
        wg_wait<0>();
      }
      if (signaller) mbar_arrive_cluster(rbars + 8 * (BAR_EMPTY2 + 4));
      e4(1);
      if (MODE == 0) {
        wg_wait<0>();
        if (signaller) mbar_arrive_cluster(rbars + 8 * BAR_EMPTY2);
      }
      PROF(6 + wg);
    }
    }

    if (MODE != 1) {
      int s = MODE == 0, ph = 0;
#pragma unroll 1
      for (int kb = s; kb < STAG; kb++) {
        mbar_wait(bars + 8 * (BAR_FULL2 + s), ph);
        if (kb == 1) PROF(8 + wg);
        if (warp == 4) PROF2(40 + kb);
        g2_step(s, kb);
        wg_wait<0>();
        if (kb < 16 - NS2 && signaller) mbar_arrive_cluster(rbars + 8 * (BAR_EMPTY2 + s));
        if (++s == NS2) { s = 0; ph ^= 1; }
      }
      {
        if (wg == 0) nb_sync(NB_LEAD, 256);
#pragma unroll
        for (int kb = STAG; kb < 16; kb++) {
          mbar_wait(bars + 8 * (BAR_FULL2 + kb % NS2), (kb / NS2) & 1);
          g2_step(kb % NS2, 1);
        }
        if (wg == 1) nb_arrive(NB_LEAD, 256);
      }
      wg_wait<0>();
      fence_regs(acc);
      PROF(10 + wg);
      const int lr = lane & 7, lm = lane >> 3;
      const uint32_t wbase = sb + warp * 2048;
      const uint32_t base = wbase + (lr + 8 * (lm & 1)) * 128;
#pragma unroll
      for (int j = 0; j < 16; j += 2) {
        const uint32_t a = base + (j >> 3) * 16384 + ((((j & 7) + (lm >> 1)) ^ lr) << 4);
        stsm4(a, pack_bf16(acc[4 * j], acc[4 * j + 1]), pack_bf16(acc[4 * j + 2], acc[4 * j + 3]),
              pack_bf16(acc[4 * j + 4], acc[4 * j + 5]), pack_bf16(acc[4 * j + 6], acc[4 * j + 7]));
      }
      __syncwarp();
      {
        const int rr = lane >> 4, ck = lane & 7, hf = (lane >> 3) & 1;
        uint4* og = reinterpret_cast<uint4*>(p.out + (size_t)(2 * ((rb2 & 7) * 128 + warp * 16 + rr) + (rb2 >> 3)) * (2 * DM) + DM + cb2 * 128 + hf * 64 + ck * 8);
        uint4 v[8];
#pragma unroll
        for (int i = 0; i < 8; i++) v[i] = lds128(wbase + hf * 16384 + (2 * i + rr) * 128 + ((ck ^ ((2 * i + rr) & 7)) << 4));
#pragma unroll
        for (int i = 0; i < 8; i++) og[(size_t)i * 4 * (2 * DM / 8)] = v[i];
      }
      PROF(12 + wg);
    }
    cluster_sync_all();
  }
}

typedef CUresult (*EncodeFn)(CUtensorMap*, CUtensorMapDataType, cuuint32_t, void*, const cuuint64_t*, const cuuint64_t*,
                             const cuuint32_t*, const cuuint32_t*, CUtensorMapInterleave, CUtensorMapSwizzle,
                             CUtensorMapL2promotion, CUtensorMapFloatOOBfill);

void make_map(EncodeFn enc, CUtensorMap* tm, const void* base, int rank, const cuuint64_t* dims, const cuuint64_t* strides,
              const cuuint32_t* box, CUtensorMapSwizzle swz) {
  cuuint32_t es[5] = {1, 1, 1, 1, 1};
  enc(tm, CU_TENSOR_MAP_DATA_TYPE_BFLOAT16, rank, const_cast<void*>(base), dims, strides, box, es,
      CU_TENSOR_MAP_INTERLEAVE_NONE, swz, CU_TENSOR_MAP_L2_PROMOTION_L2_256B, CU_TENSOR_MAP_FLOAT_OOB_FILL_NONE);
}

}

extern "C" void kernel_launch(void* const* d_in, const int* in_sizes, int n_in, void* d_out, int out_size) {
  static EncodeFn enc = nullptr;
  static bool coresident = true;
  if (!enc) {
    void* fn = nullptr;
    cudaDriverEntryPointQueryResult qr;
    cudaGetDriverEntryPoint("cuTensorMapEncodeTiled", &fn, cudaEnableDefault, &qr);
    enc = (EncodeFn)fn;
    cudaFuncSetAttribute(fused_kernel<0>, cudaFuncAttributeMaxDynamicSharedMemorySize, SMEM_BYTES);
    cudaFuncSetAttribute(fused_kernel<1>, cudaFuncAttributeMaxDynamicSharedMemorySize, SMEM_BYTES);
    cudaFuncSetAttribute(fused_kernel<2>, cudaFuncAttributeMaxDynamicSharedMemorySize, SMEM_BYTES);
    cudaLaunchConfig_t cfg = {};
    cfg.gridDim = dim3(NCTA);
    cfg.blockDim = dim3(NTHREADS);
    cfg.dynamicSmemBytes = SMEM_BYTES;
    cudaLaunchAttribute at;
    at.id = cudaLaunchAttributeClusterDimension;
    at.val.clusterDim.x = 2;
    at.val.clusterDim.y = 1;
    at.val.clusterDim.z = 1;
    cfg.attrs = &at;
    cfg.numAttrs = 1;
    int nclusters = 0;
    if (cudaOccupancyMaxActiveClusters(&nclusters, fused_kernel<0>, &cfg) == cudaSuccess) coresident = nclusters >= NCTA / 2;
    (void)cudaGetLastError();
  }
  CUtensorMap tmX, tmW, tmWo, tmQ, tmXh, tmWh;
  {
    cuuint64_t dims[3] = {1024, 2, 1024};
    cuuint64_t str[2] = {2048, 4096};
    cuuint32_t box[3] = {64, 1, 128};
    make_map(enc, &tmX, d_in[6], 3, dims, str, box, CU_TENSOR_MAP_SWIZZLE_128B);
  }
  {
    cuuint64_t dims[3] = {1024, 1024, 3};
    cuuint64_t str[2] = {6144, 2048};
    cuuint32_t box[3] = {64, 32, 3};
    make_map(enc, &tmW, d_in[7], 3, dims, str, box, CU_TENSOR_MAP_SWIZZLE_128B);
  }
  {
    cuuint64_t dims[3] = {64, 1024, 16};
    cuuint64_t str[2] = {2048, 128};
    cuuint32_t box[3] = {64, 64, 2};
    make_map(enc, &tmWo, d_in[8], 3, dims, str, box, CU_TENSOR_MAP_SWIZZLE_128B);
  }
  {
    cuuint64_t dims[5] = {1024, 2, 2, 8, 64};
    cuuint64_t str[4] = {2048, 16 * 2048, 2 * 2048, 32 * 2048};
    cuuint32_t box[5] = {16, 2, 2, 8, 4};
    make_map(enc, &tmQ, d_in[0], 5, dims, str, box, CU_TENSOR_MAP_SWIZZLE_NONE);
  }
  {
    cuuint64_t dims[4] = {1024, 256, 2, 4};
    cuuint64_t str[3] = {4096, 2048, 256 * 4096};
    cuuint32_t box[4] = {64, 8, 2, 4};
    make_map(enc, &tmXh, d_in[6], 4, dims, str, box, CU_TENSOR_MAP_SWIZZLE_128B);
  }
  {
    cuuint64_t dims[3] = {64, 1024, 48};
    cuuint64_t str[2] = {6144, 128};
    cuuint32_t box[3] = {64, 64, 4};
    make_map(enc, &tmWh, d_in[7], 3, dims, str, box, CU_TENSOR_MAP_SWIZZLE_128B);
  }
  Params p;
  p.q = (const __nv_bfloat16*)d_in[0];
  p.k = (const __nv_bfloat16*)d_in[1];
  p.v = (const __nv_bfloat16*)d_in[2];
  p.shift_k = (const __nv_bfloat16*)d_in[3];
  p.ssm_k = (const __nv_bfloat16*)d_in[4];
  p.ssm_D = (const __nv_bfloat16*)d_in[5];
  p.x = (const __nv_bfloat16*)d_in[6];
  p.w = (const __nv_bfloat16*)d_in[7];
  p.wo = (const __nv_bfloat16*)d_in[8];
  p.out = (__nv_bfloat16*)d_out;
  if (coresident) {
    fused_kernel<0><<<NCTA, NTHREADS, SMEM_BYTES>>>(p, tmX, tmW, tmWo, tmQ, tmXh, tmWh);
  } else {
    fused_kernel<0><<<4, NTHREADS, SMEM_BYTES>>>(p, tmX, tmW, tmWo, tmQ, tmXh, tmWh);
    fused_kernel<1><<<NCTA, NTHREADS, SMEM_BYTES>>>(p, tmX, tmW, tmWo, tmQ, tmXh, tmWh);
    fused_kernel<2><<<NCTA, NTHREADS, SMEM_BYTES>>>(p, tmX, tmW, tmWo, tmQ, tmXh, tmWh);
  }
}
```

```cpp
#include <cuda_runtime.h>
#include <cuda.h>
#include <cuda_bf16.h>
#include <stdint.h>

namespace {

constexpr int SEQ = 2048;
constexpr int DM = 1024;
constexpr int NCTA = 132;
constexpr int NTHREADS = 384;

constexpr int STG1A = 32768;
constexpr int NS1A = 3;
constexpr int STG1B = 12288;
constexpr int NS1B = 5;
constexpr int OFF_1B = NS1A * STG1A;
constexpr int STG2 = 32768;
constexpr int NS2 = 5;
constexpr int STGH = 73728;
constexpr int OFF_VP = 0;
constexpr int OFF_OP = 1 * STG2;
constexpr int OFF_Q = 2 * STG2;
constexpr int T_A4 = 0, T_TW = 16384, T_B2 = 24576, T_A1 = 28672, T_END = 32768;
constexpr int OFF_U = 163840;
constexpr int OFF_H = OFF_U + 32768;
constexpr int OFF_T = OFF_U - T_END;
constexpr int OFF_LAND = 4 * STG2;
constexpr int OFF_BAR = OFF_H + 32768;
constexpr int OFF_SC = OFF_BAR + 512;
constexpr int HALO = 2048;
constexpr int SMEM_BYTES = HALO + OFF_BAR + 1024;
static_assert(OFF_T + T_A1 == OFF_1B + NS1B * STG1B && OFF_T + T_TW == OFF_1B + 4 * STG1B && OFF_LAND == OFF_T + T_A4, "layout");
static_assert(3 * STGH <= OFF_BAR && SMEM_BYTES <= 232448, "smem");

constexpr int BAR_FULLA = 0;
constexpr int BAR_EMPTYA = 3;
constexpr int BAR_FULLB = 6;
constexpr int BAR_EMPTYB = 11;
constexpr int BAR_FULL2 = 16;
constexpr int BAR_EMPTY2 = 21;
constexpr int BAR_T = 26;
constexpr int BAR_UH = 27;
constexpr int BAR_LFREE = 28;
constexpr int BAR_LAND = 29;
constexpr int BAR_U = 30;
constexpr int BAR_Q = 31;
constexpr int BAR_STG = 32;
constexpr int BAR_DEAD = 33;
constexpr int BAR_X = 35;
constexpr int BAR_REL = 36;

constexpr int NB_G1DONE = 1;
constexpr int NB_OREADY = 2;
constexpr int NB_WG = 4;
constexpr int NB_HELP3 = 6;
constexpr int NB_FIRST = 7;
constexpr int NB_LEAD = 8;

constexpr int REG_MATH = 224, REG_HELP = 56;
constexpr int PF0 = 20;
constexpr uint32_t PACE = 390;
constexpr int STAG = 12;
constexpr int SPIN_LIMIT = 1 << 20;

__device__ __align__(1024) __nv_bfloat16 g_o[SEQ * DM];
__device__ __align__(128) uint32_t g_flag_o[256];
__device__ uint32_t g_flag_h[4];
__device__ uint4 g_halo[128 * 128];
__device__ __align__(128) const uint32_t g_tab[T_END / 4] = {
0x4a3a49fd,0x4acb4a1e,0x4906494e,0x48394928,0x4aa94a73,0x4bb74b55,0x486e48bb,0x443b4668,0x4b0a4adc,0x4c004bf0,0x4799481e,0xb54d3fe2,
0x4b5c4b35,0x4b9f4be4,0x464546f1,0xc4dec141,0x4b434a3e,0x4b9e4a5d,0x46b84901,0x44e448d9,0x4bfd4bdb,0x4b754bff,0xba934213,0xc5cbb7a8,
0x4ae14ba8,0x47f14a10,0xc816c4a2,0xcaf2c939,0x482e49b2,0xc12841b0,0xcad2c99e,0xcbe5cbdf,0x4bdc4a7b,0x4bfc4a98,0x41fa48b1,0x3c2b4888,
0x4a2c4bc0,0x48444b20,0xc917c3f1,0xcac5c745,0x2bdb46da,0xc7d5367b,0xcc00cb3b,0xcafacbff,0xca22c6be,0xcc00caef,0xc923cb41,0x3376c7fb,
0x4bfd4ab4,0x4bdf4acf,0xbb5c485e,0xc1bd4834,0x43b44a28,0xbcdb48e3,0xcbc4c91c,0xcbfaca55,0xcad9c61d,0xcbffc9ca,0xc824cb65,0xb744c985,
0xc9fbcbf7,0xc03cca18,0x49503dd5,0x4bee492f,0x4ba34ae9,0x4b494b01,0xc4c64809,0xc69b47ba,0xc62846c3,0xc93d42d8,0xcb62cb40,0xca0ccbd1,
0xcb12cb88,0xc84ecbfb,0x477dc567,0x4abe3ca9,0x4861c3fd,0x4bb045a8,0x4ab24bbf,0x446c4b7c,0x4ad44b19,0x4a444b30,0xc82c4761,0xc8fa4707,
0xcadfad7f,0xcbcfc32e,0xc819cc00,0xc2f0cbcc,0xbac5cb0f,0x4724c8ed,0x4bfd4788,0x4b294a4e,0x4b444a9f,0x46a14c00,0xc6b2487e,0xcb48b484,
0x499c4b45,0x48de4b5a,0xc9b446ad,0xca594651,0xcbf6c6eb,0xcb4ec8f5,0x3e6bcb37,0x4684ca48,0x4aa2c3cd,0x4bfa4172,0x48784bc2,0x3cf44be2,
0xc47e4a75,0xcab74520,0xcbaec8b9,0xc859cb94,0x480e4b6d,0x465c4b7f,0xcae545f4,0xcb574596,0xc9eaca36,0xc7dbcb2a,0x4963c90b,0x4af8c71e,
0x4b3f4871,0x48a24ac1,0xc6c94aa8,0xca864849,0xcbedc48a,0xc949ca46,0x4061cbac,0x4a01c8f7,0x44844b90,0x41344ba0,0xcbad4537,0xcbe544d8,
0xc22ccbc5,0x3ffbcc00,0x4bdac39c,0x4bf0b4e9,0x3e844bea,0xc66d4bb6,0xcbf540b8,0xcb53c441,0xb11bcbfd,0x492acaca,0x4c00bb2a,0x4a1c483c,
0x39344baf,0xbd3f4bbc,0xcbfe4478,0xcbf94417,0x46e0cbd6,0x4988cb4c,0x4b394269,0x49c84690,0xca684a30,0xcbf04734,0xc8cac912,0xc00acb25,
0x4be7c63a,0x4acd42cc,0x41034b5f,0xc8364bd1,0xc2824bc8,0xc5264bd3,0xcbd5436b,0xcb9342a7,0x4b10ca66,0x4be3c931,0x478348cd,0x41664a16,
0xcb673a61,0xc8f2c5bf,0x4611cbfd,0x4a4acb77,0x44cc49e4,0xc6564bef,0xcba2496a,0xcb584023,0xc6f64bdd,0xc8564be6,0xcb3441e2,0xcab9411c,
0x4be9c777,0x4b23c42f,0xc0c54b13,0xc73a4bb9,0xc0d1c9a7,0x45b3cb76,0x4be9c9a9,0x4b7ac5c5,0xcb334b15,0xcbbb474b,0xc6fcc772,0x441dcb1f,
0xc9214bed,0xc9d74bf3,0xca244055,0xc9783f1a,0x49a5b998,0x472941a4,0xc9ab4bfe,0xcb274be0,0x4a2acbfe,0x4be0cb26,0x49193a2f,0x4197472f,
0xc883c07a,0x3f33c97a,0x4a9bcbec,0x4bf3c9d5,0xca774bf8,0xcafe4bfc,0xc8b63d8a,0xc7c53bf2,0x409f4634,0xc18b48a4,0xcbeb4b60,0xcbe14a84,
0x4b8bc914,0x4940c447,0xc5554a2e,0xca0a4bb5,0x49e0cbd6,0x4bffcb56,0x496ec276,0x386b4662,0xcb6b4bff,0xcbba4c00,0xc5ff38cf,0xc42332ad,
0xc79349f5,0xc9cf4afb,0xcb0c4957,0xc98147d0,0x425d40ac,0xc4f64846,0xcbd74bea,0xcb9b4ac3,0x4a3cc829,0x41c93c44,0xc9034ad5,0xcbde4bfb,
0xcbec4c00,0xcc004bff,0xc06eb1e4,0xb420b89d,0xcb3d4bab,0xcbf14bfb,0xc6cf4490,0xbfb03c5e,0xc9e84aa6,0xcbcd4be2,0xc9654873,0xc322417f,
0xc80b4908,0xcb924bb2,0xcae74a38,0xc52c4460,0xcbf44bfc,0xcbca4bf9,0x3ecfbbc0,0x4346bd71,0xcbd84be8,0xcaf44b73,0x4251c0de,0x47ebc5d7,
0xcbaa4bc3,0xc98a4a4f,0x4496c3c0,0x49c6c8eb,0xcb6c4b8d,0xc75648a7,0x45fac549,0x4b1cca82,0xcb824bf4,0xcb1d4bee,0x4584bf01,0x4750c048,
0xc95c4aa1,0xc673497c,0x49f1c87b,0x4b52c9d3,0xc3e5478e,0x44353cc2,0x4bc1cb0d,0x4bb8cbfa,0x43772f12,0x4a7fc890,0x4bc7cc00,0x48acca93,
0xca9d4be6,0xca034bde,0x4880c10f,0x4947c1d5,0xbe204813,0x431544f0,0x4bf7cae2,0x4bcdcb9c,0x49a3c561,0x4bb4c983,0x49aecb89,0x4454c9cc,
0x4bf8cb83,0x4993cbba,0xbda3c57e,0xc9bd4429,0xc9534bd4,0xc88d4bc9,0x49f9c29b,0x4a94c35f,0x48213dee,0x4a12c016,0x4adacbf7,0x4936cbef,
0x4bc5cb64,0x49d1cbff,0xc3a8c622,0xc97e3616,0x3b8ec91e,0xc8dcbd26,0xcbfc4a26,0xca5b4bf9,0xc76c4bbd,0xc5a24baf,0x4b16c411,0x4b7dc472,
0x4b66c579,0x4bfbc851,0x4617cb85,0x3c90cabc,0x44b4cb3c,0xc2e4c93b,0xcba646d4,0xcbd04a0e,0xcbd54811,0xcb004b4b,0xc28e4ae4,0x47bf4696,
0xc3834ba1,0xbf4c4b91,0x4bc7c4d2,0x4bf3c531,0x4bc1c9b0,0x4ac0cac8,0xc3d9c9a0,0xc84cc83e,0xc95ac4a8,0xcb963fc9,0xc9f34ba7,0xc5144bf1,
0xc58a4bdb,0x459c498e,0x4b81c207,0x4b7ec9c1,0x30524b80,0x402f4b6e,0x4c00c590,0x4beec5ee,0x4910cb8c,0x45b9cbf2,0xca32c54f,0xcb78bf7e,
0xcbda481c,0xca144a8a,0x421f4add,0x4934489d,0x4b0440ea,0x4bd3c718,0x47afcbe8,0xc2b3cb2c,0x44054b5b,0x45e24b47,0x4bbec64b,0x4b70c6a7,
0x39fdcbf5,0xc44ecb95,0xcbfe3e9d,0xcbb5451a,0xc5734bd8,0x415a4bcf,0x4b864244,0x4be3c2fd,0x48d4cb07,0xbc12cbf2,0xca61c7a4,0xcbfc3f65,
0x47a94b31,0x48a94b1b,0x4b06c702,0x4a80c75c,0xc876cad7,0xca51c9c4,0xcaa44826,0xc8e8498c,0x490d4a6e,0x4b7447e6,0x4a34c8c3,0x45d1caf5,
0xc99ac9f7,0xcbf9c33a,0xc9b74955,0xbd584bcb,0x496c4b03,0x4a1a4aea,0x49e2c7b4,0x492dc806,0xcb8ac869,0xcbffc5ae,0xc55b4aad,0xb5b24b7b,
0x4beb3e52,0x4a53c502,0xc093cbf6,0xc8e6cb99,0xca794605,0xc3524abb,0x48b44b69,0x4bca4854,0x4ab04ad0,0x4b2d4ab6,0x4863c831,0x4713c85c,
0xcba6c086,0xca883d0d,0x44ae4beb,0x489f4bfa,0x462ec95e,0xbf97cb50,0xcb61c9ef,0xcbf2c67f,0x47674bfe,0x4b6f4a57,0x4b18b966,0x45e8c8e1,
0x4b8e4a9a,0x4bd24a7d,0x4543c885,0x42bfc8ae,0xc8c044ba,0xc4fc47f6,0x4a704ba5,0x4b9a4af0,0xc8becc00,0xcb4dcb51,0xca72a248,0xc68a4679,
0x4b8f44c0,0x4803c4ea,0xc53dcba4,0xcaeccb9d,0x4bf84a5f,0x4bff4a40,0x3dbcc8d7,0xb839c8fe,0x28b64967,0x450e4a91,0x4c0049e6,0x4b974892,
0xcbf7c961,0xca8fc508,0x3e0749ec,0x48954b98,0xc1eeca65,0xca42cbff,0xcbddc8cf,0xc8fcb806,0x4be74a20,0x4bb149ff,0xc0f6c925,0xc466c94b,
0x48c84b68,0x4a8d4be4,0x4a6a460b,0x4897414d,0xc6e53e39,0x3c7747e0,0x4b384bf6,0x4bfb4af7,0xcbfecaaf,0xc9d9c5dc,0x39014866,0x49754b72,
0x4b5d49de,0x4aed49bb,0xc63fc971,0xc800c995,0x4ba94bfd,0x4bff4bb3,0x449cbaf8,0xb6dfc45a,0x486b4a6c,0x4b224bce,0x4aab48c5,0x47404309,
0xbee84390,0x488b4a05,0x4bf44bc6,0x4a964944,0x4a634997,0x49bf4973,0xc8d2c9b9,0xc991c9db,0x4b874b09,0x4a4c4a08,0xc56dc79e,0xc8f0c942,
0x4bfe4bd9,0x4ac64a8b,0xb9cac238,0xc841c89a,0x4bbe4bf5,0x4b2e4afd,0x440b3eb6,0xc70dc7ca,0x4a3a49fd,0xcacbca1e,0x4906494e,0xc839c928,
0x4aa94a73,0xcbb7cb55,0x486e48bb,0xc43bc668,0x4b0a4adc,0xcc00cbf0,0x4799481e,0x354dbfe2,0x4b5c4b35,0xcb9fcbe4,0x464546f1,0x44de4141,
0x4b434a3e,0xcb9eca5d,0x46b84901,0xc4e4c8d9,0x4bfd4bdb,0xcb75cbff,0xba934213,0x45cb37a8,0x4ae14ba8,0xc7f1ca10,0xc816c4a2,0x4af24939,
0x482e49b2,0x4128c1b0,0xcad2c99e,0x4be54bdf,0x4bdc4a7b,0xcbfcca98,0x41fa48b1,0xbc2bc888,0x4a2c4bc0,0xc844cb20,0xc917c3f1,0x4ac54745,
0x2bdb46da,0x47d5b67b,0xcc00cb3b,0x4afa4bff,0xca22c6be,0x4c004aef,0xc923cb41,0xb37647fb,0x4bfd4ab4,0xcbdfcacf,0xbb5c485e,0x41bdc834,
0x43b44a28,0x3cdbc8e3,0xcbc4c91c,0x4bfa4a55,0xcad9c61d,0x4bff49ca,0xc824cb65,0x37444985,0xc9fbcbf7,0x403c4a18,0x49503dd5,0xcbeec92f,
0x4ba34ae9,0xcb49cb01,0xc4c64809,0x469bc7ba,0xc62846c3,0x493dc2d8,0xcb62cb40,0x4a0c4bd1,0xcb12cb88,0x484e4bfb,0x477dc567,0xcabebca9,
0x4861c3fd,0xcbb0c5a8,0x4ab24bbf,0xc46ccb7c,0x4ad44b19,0xca44cb30,0xc82c4761,0x48fac707,0xcadfad7f,0x4bcf432e,0xc819cc00,0x42f04bcc,
0xbac5cb0f,0xc72448ed,0x4bfd4788,0xcb29ca4e,0x4b444a9f,0xc6a1cc00,0xc6b2487e,0x4b483484,0x499c4b45,0xc8decb5a,0xc9b446ad,0x4a59c651,
0xcbf6c6eb,0x4b4e48f5,0x3e6bcb37,0xc6844a48,0x4aa2c3cd,0xcbfac172,0x48784bc2,0xbcf4cbe2,0xc47e4a75,0x4ab7c520,0xcbaec8b9,0x48594b94,
0x480e4b6d,0xc65ccb7f,0xcae545f4,0x4b57c596,0xc9eaca36,0x47db4b2a,0x4963c90b,0xcaf8471e,0x4b3f4871,0xc8a2cac1,0xc6c94aa8,0x4a86c849,
0xcbedc48a,0x49494a46,0x4061cbac,0xca0148f7,0x44844b90,0xc134cba0,0xcbad4537,0x4be5c4d8,0xc22ccbc5,0xbffb4c00,0x4bdac39c,0xcbf034e9,
0x3e844bea,0x466dcbb6,0xcbf540b8,0x4b534441,0xb11bcbfd,0xc92a4aca,0x4c00bb2a,0xca1cc83c,0x39344baf,0x3d3fcbbc,0xcbfe4478,0x4bf9c417,
0x46e0cbd6,0xc9884b4c,0x4b394269,0xc9c8c690,0xca684a30,0x4bf0c734,0xc8cac912,0x400a4b25,0x4be7c63a,0xcacdc2cc,0x41034b5f,0x4836cbd1,
0xc2824bc8,0x4526cbd3,0xcbd5436b,0x4b93c2a7,0x4b10ca66,0xcbe34931,0x478348cd,0xc166ca16,0xcb673a61,0x48f245bf,0x4611cbfd,0xca4a4b77,
0x44cc49e4,0x4656cbef,0xcba2496a,0x4b58c023,0xc6f64bdd,0x4856cbe6,0xcb3441e2,0x4ab9c11c,0x4be9c777,0xcb23442f,0xc0c54b13,0x473acbb9,
0xc0d1c9a7,0xc5b34b76,0x4be9c9a9,0xcb7a45c5,0xcb334b15,0x4bbbc74b,0xc6fcc772,0xc41d4b1f,0xc9214bed,0x49d7cbf3,0xca244055,0x4978bf1a,
0x49a5b998,0xc729c1a4,0xc9ab4bfe,0x4b27cbe0,0x4a2acbfe,0xcbe04b26,0x49193a2f,0xc197c72f,0xc883c07a,0xbf33497a,0x4a9bcbec,0xcbf349d5,
0xca774bf8,0x4afecbfc,0xc8b63d8a,0x47c5bbf2,0x409f4634,0x418bc8a4,0xcbeb4b60,0x4be1ca84,0x4b8bc914,0xc9404447,0xc5554a2e,0x4a0acbb5,
0x49e0cbd6,0xcbff4b56,0x496ec276,0xb86bc662,0xcb6b4bff,0x4bbacc00,0xc5ff38cf,0x4423b2ad,0xc79349f5,0x49cfcafb,0xcb0c4957,0x4981c7d0,
0x425d40ac,0x44f6c846,0xcbd74bea,0x4b9bcac3,0x4a3cc829,0xc1c9bc44,0xc9034ad5,0x4bdecbfb,0xcbec4c00,0x4c00cbff,0xc06eb1e4,0x3420389d,
0xcb3d4bab,0x4bf1cbfb,0xc6cf4490,0x3fb0bc5e,0xc9e84aa6,0x4bcdcbe2,0xc9654873,0x4322c17f,0xc80b4908,0x4b92cbb2,0xcae74a38,0x452cc460,
0xcbf44bfc,0x4bcacbf9,0x3ecfbbc0,0xc3463d71,0xcbd84be8,0x4af4cb73,0x4251c0de,0xc7eb45d7,0xcbaa4bc3,0x498aca4f,0x4496c3c0,0xc9c648eb,
0xcb6c4b8d,0x4756c8a7,0x45fac549,0xcb1c4a82,0xcb824bf4,0x4b1dcbee,0x4584bf01,0xc7504048,0xc95c4aa1,0x4673c97c,0x49f1c87b,0xcb5249d3,
0xc3e5478e,0xc435bcc2,0x4bc1cb0d,0xcbb84bfa,0x43772f12,0xca7f4890,0x4bc7cc00,0xc8ac4a93,0xca9d4be6,0x4a03cbde,0x4880c10f,0xc94741d5,
0xbe204813,0xc315c4f0,0x4bf7cae2,0xcbcd4b9c,0x49a3c561,0xcbb44983,0x49aecb89,0xc45449cc,0x4bf8cb83,0xc9934bba,0xbda3c57e,0x49bdc429,
0xc9534bd4,0x488dcbc9,0x49f9c29b,0xca94435f,0x48213dee,0xca124016,0x4adacbf7,0xc9364bef,0x4bc5cb64,0xc9d14bff,0xc3a8c622,0x497eb616,
0x3b8ec91e,0x48dc3d26,0xcbfc4a26,0x4a5bcbf9,0xc76c4bbd,0x45a2cbaf,0x4b16c411,0xcb7d4472,0x4b66c579,0xcbfb4851,0x4617cb85,0xbc904abc,
0x44b4cb3c,0x42e4493b,0xcba646d4,0x4bd0ca0e,0xcbd54811,0x4b00cb4b,0xc28e4ae4,0xc7bfc696,0xc3834ba1,0x3f4ccb91,0x4bc7c4d2,0xcbf34531,
0x4bc1c9b0,0xcac04ac8,0xc3d9c9a0,0x484c483e,0xc95ac4a8,0x4b96bfc9,0xc9f34ba7,0x4514cbf1,0xc58a4bdb,0xc59cc98e,0x4b81c207,0xcb7e49c1,
0x30524b80,0xc02fcb6e,0x4c00c590,0xcbee45ee,0x4910cb8c,0xc5b94bf2,0xca32c54f,0x4b783f7e,0xcbda481c,0x4a14ca8a,0x421f4add,0xc934c89d,
0x4b0440ea,0xcbd34718,0x47afcbe8,0x42b34b2c,0x44054b5b,0xc5e2cb47,0x4bbec64b,0xcb7046a7,0x39fdcbf5,0x444e4b95,0xcbfe3e9d,0x4bb5c51a,
0xc5734bd8,0xc15acbcf,0x4b864244,0xcbe342fd,0x48d4cb07,0x3c124bf2,0xca61c7a4,0x4bfcbf65,0x47a94b31,0xc8a9cb1b,0x4b06c702,0xca80475c,
0xc876cad7,0x4a5149c4,0xcaa44826,0x48e8c98c,0x490d4a6e,0xcb74c7e6,0x4a34c8c3,0xc5d14af5,0xc99ac9f7,0x4bf9433a,0xc9b74955,0x3d58cbcb,
0x496c4b03,0xca1acaea,0x49e2c7b4,0xc92d4806,0xcb8ac869,0x4bff45ae,0xc55b4aad,0x35b2cb7b,0x4beb3e52,0xca534502,0xc093cbf6,0x48e64b99,
0xca794605,0x4352cabb,0x48b44b69,0xcbcac854,0x4ab04ad0,0xcb2dcab6,0x4863c831,0xc713485c,0xcba6c086,0x4a88bd0d,0x44ae4beb,0xc89fcbfa,
0x462ec95e,0x3f974b50,0xcb61c9ef,0x4bf2467f,0x47674bfe,0xcb6fca57,0x4b18b966,0xc5e848e1,0x4b8e4a9a,0xcbd2ca7d,0x4543c885,0xc2bf48ae,
0xc8c044ba,0x44fcc7f6,0x4a704ba5,0xcb9acaf0,0xc8becc00,0x4b4d4b51,0xca72a248,0x468ac679,0x4b8f44c0,0xc80344ea,0xc53dcba4,0x4aec4b9d,
0x4bf84a5f,0xcbffca40,0x3dbcc8d7,0x383948fe,0x28b64967,0xc50eca91,0x4c0049e6,0xcb97c892,0xcbf7c961,0x4a8f4508,0x3e0749ec,0xc895cb98,
0xc1eeca65,0x4a424bff,0xcbddc8cf,0x48fc3806,0x4be74a20,0xcbb1c9ff,0xc0f6c925,0x4466494b,0x48c84b68,0xca8dcbe4,0x4a6a460b,0xc897c14d,
0xc6e53e39,0xbc77c7e0,0x4b384bf6,0xcbfbcaf7,0xcbfecaaf,0x49d945dc,0x39014866,0xc975cb72,0x4b5d49de,0xcaedc9bb,0xc63fc971,0x48004995,
0x4ba94bfd,0xcbffcbb3,0x449cbaf8,0x36df445a,0x486b4a6c,0xcb22cbce,0x4aab48c5,0xc740c309,0xbee84390,0xc88bca05,0x4bf44bc6,0xca96c944,
0x4a634997,0xc9bfc973,0xc8d2c9b9,0x499149db,0x4b874b09,0xca4cca08,0xc56dc79e,0x48f04942,0x4bfe4bd9,0xcac6ca8b,0xb9cac238,0x4841489a,
0x4bbe4bf5,0xcb2ecafd,0x440b3eb6,0x470d47ca,0x4b9e4b7f,0x4a9d4b31,0x44e44596,0xc880c702,0x4bcf4bb9,0x491049e6,0x42f0442f,0xca32c967,
0x4bf04be2,0x462e481e,0x400a417f,0xcb61cadc,0x4bff4bf9,0x3ee843fd,0x386b3d26,0xcbf4cbbf,0x3c2b44d8,0xc9f9c7b4,0xcbfccba0,0xc953cb03,
0xc684c1a4,0xcbfecb68,0xcb4ecbe0,0xb9fdc60b,0xca4ac8eb,0xca72cba8,0xc8f2ca4f,0x48be44a2,0xcbdecb4b,0xc40bc87e,0xc1c9c696,0x4bbe4a9f,
0xcbdfcbbc,0xc76ccad0,0x41bdc417,0x4b164831,0xc7dbca84,0x48763af8,0x4af848a4,0x4aa44bfd,0x45b3bcc2,0x4bf74b3b,0x4b7a4bfa,0xbe0746da,
0x4b9249c1,0x46454a75,0x452c498e,0xcb5cc8b9,0x469bc2a7,0x4bc74885,0x4b494bd3,0x43834a9a,0x4bf04afb,0x455b4b09,0xbffb47d0,0xcb8ac79e,
0x419749cc,0xcb38c61d,0xcbe0c983,0xc6e5cb65,0xcb1cc718,0xc82ecbac,0xc756cb2c,0x4ad2448a,0x4a444be6,0xb0524a5f,0xc8fa411c,0xcc00c8d7,
0xc9883c5e,0xcba6ca73,0xc9c8cbfb,0x44aec8bb,0xc940cbff,0x486bc567,0x4a0a3616,0x4aab4b88,0x4a7f3f65,0x49234bfd,0x48ac4bf2,0xca223b2a,
0xca593f1a,0xcbbec925,0xc8decbf3,0x4405ca20,0xc166cb73,0x4a70c213,0x4be345d7,0x48c04bdb,0x4b9b4a0e,0xb9ca4b0f,0xc4f6493b,0xcbfec788,
0xc9bd433a,0xc9fbcb5f,0xc993cbcb,0x4950c63a,0xc65ccbfc,0x47a9c9de,0x4b57bbf2,0x4b064971,0x4b2349d3,0xa8b64bc0,0xc73a497c,0xcc00c3f1,
0xcbcdbfc9,0xc799cbc2,0xc322cbf1,0x4b0ac3cd,0x48dcc854,0x4ab249e4,0x4a5b4abb,0xc861496a,0x4be5b2ad,0x49e249b9,0x41344c00,0xc96c4997,
0xcb2744f0,0xca6ac91c,0xc729cb9c,0x48c8ca28,0x49c6c89d,0x4ae14871,0x498a4a8a,0xc8164aa8,0xc7bf4a57,0xcb44c772,0xcb00c8e1,0x46b2cb15,
0xbd3f4bff,0xcab0494e,0xcbf9b89d,0xc863c9fd,0x418bcbef,0x4ba9c6c3,0x4be14016,0x449c4b40,0xc4354bcf,0xcc0040b8,0xcbb8c2fd,0xabdbcbea,
0x459ccb9d,0x4bae407a,0x4b7e44ea,0xc47e4bec,0xcb93bd71,0xc543ca3e,0x4526cbf9,0x4b8ec901,0x49814851,0xc56d4c00,0xc9cf4abc,0xcb87ad7f,
0xc454caf5,0x4ad9ca30,0x4bb4c7e6,0x48244912,0xc2b34bff,0xcbed4276,0xcbd33806,0x4061cbd6,0x4856cbee,0x4bf8c8b1,0x4ab94048,0x3dbc4a7b,
0xcbf1483e,0xc86ec6eb,0xbfb0cac8,0x4aa9cb37,0x49d14502,0xc77d4bfd,0xc97e4b99,0xcb123a61,0x3c12cb72,0x4c00c829,0x4bfcc5dc,0x311b4ad5,
0x497841d5,0xc0f64ab4,0xc9d74bde,0xcbe7485e,0x47ebcbf2,0x4bfdc90b,0x4af4bf7e,0xba934a36,0xcbd0467f,0xbac5c9a7,0x42e4cb50,0x4bfdc9a9,
0x3d584a05,0xcbe74a38,0xcbf94944,0xc103c908,0xcafe4bc9,0xcb5d4809,0xc7c5c35f,0x463fcae9,0x4673451a,0xc9174bc5,0xcb524b95,0xca2c439c,
0x4b96cb51,0x48783a2f,0x45144679,0xcaa24bfe,0xc352c7ca,0x4ba2cb8d,0x4bcacafd,0x44cc4549,0xc423c472,0x48d2cb19,0x4bbacbaf,0x4a63c761,
0xcbcd49c4,0xc3b4c269,0x4315c98c,0x4bc4cbd6,0xc9344b98,0xcb3f4914,0xca144508,0x46c9ca2e,0x45e84141,0xcb334c00,0xcb6f4be4,0xc6fc2f12,
0x4c00cb91,0x4906c6ad,0x34204531,0xca3a4b45,0x4a12cb7b,0x4b62ca66,0x4936c5ae,0xc62848cd,0x415ac7e0,0x4bf5cbea,0x4be3caf7,0x3e8440ac,
0xc80341b0,0x4a9bcb83,0x4aeccbdf,0x4883c57e,0xc34645ee,0xcb434b6d,0xcbca4b6e,0xc6b845f4,0x3c903d0d,0xcadf4b13,0xcbfb4bfa,0xc8194777,
0x45d1c309,0xca684aa6,0xcb744bce,0xc8ca4873,0x48fcc7fb,0xc9e04a26,0xca424aef,0xc96e491e,0xcb1d4b47,0xc1fa4537,0x4750c6a7,0x4bdccb90,
0xcac04af0,0x3e6b3998,0x484cc7f6,0x4bf6cbfe,0xca534a8b,0x4611c3c0,0x48e6c89a,0x4b67cbc3,0xc9d94a18,0x4903c811,0x4975c92f,0x4a3ccae4,
0x4947c75c,0x4bfdcbaf,0x4a03cb1b,0xbb5cc478,0x4b78ca91,0x49eacb60,0x45b9c892,0xc9634634,0x4bf2cbf0,0x40d1c78e,0xbf97bfe2,0xcbe94b0d,
0x4a96cb7c,0xc80b4207,0xc88b45a8,0xcae74bdb,0x488dcaea,0xc4c6c36b,0xca944806,0xcba34bc8,0xc44ec14d,0xcbda49f5,0xcbb54be4,0xc22c4957,
0xcb4d4939,0xc9194b89,0xc68a4a10,0x4a2ac561,0xcb2e4c00,0x45fa40ea,0x470db484,0x4b6ccbe8,0xcb7d485c,0xcad44bdd,0xc5a24ab6,0x482c41e2,
0xc8e84bb3,0x46e04490,0x4a51c45a,0x4b39cbab,0x4895367b,0x4b8bcb64,0x4a8fcbff,0xc555c622,0x4b9fcb94,0xc377c7a4,0xc4dec520,0xcbc74b07,
0xbf4c4a7d,0x49b44055,0x4bf3c8ae,0x499ccbed,0x4bffc942,0x4783cbe8,0x35b2ca08,0xcb1040de,0xbc77c985,0xcbd746d4,0xcbfb49ca,0xc25d4b3c,
0xcbe54a46,0x3da349f7,0x412848f7,0x4bf8c955,0x4beec8fe,0x480ecbf8,0xc02fca40,0xcae5bd8a,0xc89fc668,0xcbe9487b,0xca884b55,0x40c54aa1,
0xc7404bfb,0x49e844a8,0x4b22bca9,0x4965cba7,0x4c00c83c,0x3b8ecb69,0xb376caca,0xcbfc4605,0xc5e2c9ff,0xcbadb8cf,0xcb70494b,0xc4844bff,
0xc4fc4bff,0x49ab4813,0x4b9ab7a8,0x49a5cae2,0x4ac6ca4e,0xc496cadd,0xc841c8ed,0xcbaa481c,0xcbee42cc,0xc28e4bfe,0xc03c4bd1,0x4bd5b966,
0xca804995,0xb9344c00,0x48a949bb,0x4bfeb1e4,0x4b97c745,0x409fcbf7,0xc50ecb20,0xcbebbdee,0xcc004172,0xc3e54bd8,0x354d4be2,0x4bc14244,
0x4bb04023,0x458acba4,0x446ccbef,0xcb81c4c0,0x4a1a4973,0x4bd5bbc0,0x492dc9db,0xc282cbfc,0xca8dc8e3,0xcb0c4579,0xc8974a55,0x47934b85,
0x4af24849,0x49aec8c3,0x47f1cac1,0xc9a3ca6e,0xcb48c74b,0xc7af4a65,0xc6a14b1f,0x4b0448cf,0x4713ca1e,0xc6f6cbf4,0xcb2dc928,0xcb343f01,
0x36df4bd1,0x4b3d49a0,0x4bff42d8,0x46cfc9b0,0xc7d5cbb6,0xcbc5be52,0xcafa4441,0x43a84bf6,0x4ab749d5,0x48d4c866,0x4859c97a,0xca61caaf,
0xcbd2c8d9,0xca24410f,0xc2bf4a5d,0x49214be6,0x4a4cc32e,0xc251cb8c,0xc8f0cbcc,0xcbd8c54f,0xb7444b25,0x4ba649ef,0x4bff4734,0x44b4c95e,
0xca01cb56,0xc9b74390,0xc9494662,0x499a4bc6,0x38394a98,0x4a774bd4,0x4bff4888,0x48b6c29b,0xcbb7ca48,0xc95c3e9d,0xc43b48f5,0x49f14bf5,
0x484ec5bf,0xc95acc00,0xcabecb77,0xc9f3a248,0x492a4bfb,0x4a793eb6,0x4a1cbc44,0xc8b4cbf5,0x4bb14834,0x45ffc411,0xc466cacf,0xcb6bcbbd,
0x45cb4b2a,0x4bf74ad7,0x4b75471e,0x3e20c826,0xcb29c5c5,0x421f49ec,0x47244b76,0x4bda4961,0xc836cbb2,0xcb18c6f1,0xcacdc460,0x47674b35,
0xc800cb01,0xcbeccba1,0xcaedc7ba,0xc06e44d2,0x484434e9,0xc821caad,0xcac5cc00,0xcadac869,0x4bfa4b26,0x4573be39,0x3cf4c72f,0xcb86cbf6,
0x46564a82,0x4b8f49b2,0x4b5848a7,0xc53dc99e,0xc9bfc707,0x3ecf4590,0x49914b30,0x4bf44b80,0xcbfacb4c,0xc617c086,0x3cdb4690,0x4b664beb,
0xca86cbb5,0xca34c8c5,0xc8a2c447,0x490d4a6c,0xc41dc890,0xcbddcb41,0xcbbbca93,0x41ee46be,0x4acb4b5a,0x4b824b5b,0x48394651,0xc584c64b,
0x493d4a16,0x4bc14ba5,0x4a0c4931,0xc3d9c4ba,0x466d4846,0x4beb4bd9,0x4b534ac3,0xc093c238,0x3f334429,0x4bfe4bf7,0x4bf34bba,0xb901bdd5,
0x4b9e4b7f,0xca9dcb31,0x44e44596,0x48804702,0x4bcf4bb9,0xc910c9e6,0x42f0442f,0x4a324967,0x4bf04be2,0xc62ec81e,0x400a417f,0x4b614adc,
0x4bff4bf9,0xbee8c3fd,0x386b3d26,0x4bf44bbf,0x3c2b44d8,0x49f947b4,0xcbfccba0,0x49534b03,0xc684c1a4,0x4bfe4b68,0xcb4ecbe0,0x39fd460b,
0xca4ac8eb,0x4a724ba8,0xc8f2ca4f,0xc8bec4a2,0xcbdecb4b,0x440b487e,0xc1c9c696,0xcbbeca9f,0xcbdfcbbc,0x476c4ad0,0x41bdc417,0xcb16c831,
0xc7dbca84,0xc876baf8,0x4af848a4,0xcaa4cbfd,0x45b3bcc2,0xcbf7cb3b,0x4b7a4bfa,0x3e07c6da,0x4b9249c1,0xc645ca75,0x452c498e,0x4b5c48b9,
0x469bc2a7,0xcbc7c885,0x4b494bd3,0xc383ca9a,0x4bf04afb,0xc55bcb09,0xbffb47d0,0x4b8a479e,0x419749cc,0x4b38461d,0xcbe0c983,0x46e54b65,
0xcb1cc718,0x482e4bac,0xc756cb2c,0xcad2c48a,0x4a444be6,0x3052ca5f,0xc8fa411c,0x4c0048d7,0xc9883c5e,0x4ba64a73,0xc9c8cbfb,0xc4ae48bb,
0xc940cbff,0xc86b4567,0x4a0a3616,0xcaabcb88,0x4a7f3f65,0xc923cbfd,0x48ac4bf2,0x4a22bb2a,0xca593f1a,0x4bbe4925,0xc8decbf3,0xc4054a20,
0xc166cb73,0xca704213,0x4be345d7,0xc8c0cbdb,0x4b9b4a0e,0x39cacb0f,0xc4f6493b,0x4bfe4788,0xc9bd433a,0x49fb4b5f,0xc993cbcb,0xc950463a,
0xc65ccbfc,0xc7a949de,0x4b57bbf2,0xcb06c971,0x4b2349d3,0x28b6cbc0,0xc73a497c,0x4c0043f1,0xcbcdbfc9,0x47994bc2,0xc322cbf1,0xcb0a43cd,
0x48dcc854,0xcab2c9e4,0x4a5b4abb,0x4861c96a,0x4be5b2ad,0xc9e2c9b9,0x41344c00,0x496cc997,0xcb2744f0,0x4a6a491c,0xc729cb9c,0xc8c84a28,
0x49c6c89d,0xcae1c871,0x498a4a8a,0x4816caa8,0xc7bf4a57,0x4b444772,0xcb00c8e1,0xc6b24b15,0xbd3f4bff,0x4ab0c94e,0xcbf9b89d,0x486349fd,
0x418bcbef,0xcba946c3,0x4be14016,0xc49ccb40,0xc4354bcf,0x4c00c0b8,0xcbb8c2fd,0x2bdb4bea,0x459ccb9d,0xcbaec07a,0x4b7e44ea,0x447ecbec,
0xcb93bd71,0x45434a3e,0x4526cbf9,0xcb8e4901,0x49814851,0x456dcc00,0xc9cf4abc,0x4b872d7f,0xc454caf5,0xcad94a30,0x4bb4c7e6,0xc824c912,
0xc2b34bff,0x4bedc276,0xcbd33806,0xc0614bd6,0x4856cbee,0xcbf848b1,0x4ab94048,0xbdbcca7b,0xcbf1483e,0x486e46eb,0xbfb0cac8,0xcaa94b37,
0x49d14502,0x477dcbfd,0xc97e4b99,0x4b12ba61,0x3c12cb72,0xcc004829,0x4bfcc5dc,0xb11bcad5,0x497841d5,0x40f6cab4,0xc9d74bde,0x4be7c85e,
0x47ebcbf2,0xcbfd490b,0x4af4bf7e,0x3a93ca36,0xcbd0467f,0x3ac549a7,0x42e4cb50,0xcbfd49a9,0x3d584a05,0x4be7ca38,0xcbf94944,0x41034908,
0xcafe4bc9,0x4b5dc809,0xc7c5c35f,0xc63f4ae9,0x4673451a,0x4917cbc5,0xcb524b95,0x4a2cc39c,0x4b96cb51,0xc878ba2f,0x45144679,0x4aa2cbfe,
0xc352c7ca,0xcba24b8d,0x4bcacafd,0xc4ccc549,0xc423c472,0xc8d24b19,0x4bbacbaf,0xca634761,0xcbcd49c4,0x43b44269,0x4315c98c,0xcbc44bd6,
0xc9344b98,0x4b3fc914,0xca144508,0xc6c94a2e,0x45e84141,0x4b33cc00,0xcb6f4be4,0x46fcaf12,0x4c00cb91,0xc90646ad,0x34204531,0x4a3acb45,
0x4a12cb7b,0xcb624a66,0x4936c5ae,0x4628c8cd,0x415ac7e0,0xcbf54bea,0x4be3caf7,0xbe84c0ac,0xc80341b0,0xca9b4b83,0x4aeccbdf,0xc883457e,
0xc34645ee,0x4b43cb6d,0xcbca4b6e,0x46b8c5f4,0x3c903d0d,0x4adfcb13,0xcbfb4bfa,0x4819c777,0x45d1c309,0x4a68caa6,0xcb744bce,0x48cac873,
0x48fcc7fb,0x49e0ca26,0xca424aef,0x496ec91e,0xcb1d4b47,0x41fac537,0x4750c6a7,0xcbdc4b90,0xcac04af0,0xbe6bb998,0x484cc7f6,0xcbf64bfe,
0xca534a8b,0xc61143c0,0x48e6c89a,0xcb674bc3,0xc9d94a18,0xc9034811,0x4975c92f,0xca3c4ae4,0x4947c75c,0xcbfd4baf,0x4a03cb1b,0x3b5c4478,
0x4b78ca91,0xc9ea4b60,0x45b9c892,0x4963c634,0x4bf2cbf0,0xc0d1478e,0xbf97bfe2,0x4be9cb0d,0x4a96cb7c,0x480bc207,0xc88b45a8,0x4ae7cbdb,
0x488dcaea,0x44c6436b,0xca944806,0x4ba3cbc8,0xc44ec14d,0x4bdac9f5,0xcbb54be4,0x422cc957,0xcb4d4939,0x4919cb89,0xc68a4a10,0xca2a4561,
0xcb2e4c00,0xc5fac0ea,0x470db484,0xcb6c4be8,0xcb7d485c,0x4ad4cbdd,0xc5a24ab6,0xc82cc1e2,0xc8e84bb3,0xc6e0c490,0x4a51c45a,0xcb394bab,
0x4895367b,0xcb8b4b64,0x4a8fcbff,0x45554622,0x4b9fcb94,0x437747a4,0xc4dec520,0x4bc7cb07,0xbf4c4a7d,0xc9b4c055,0x4bf3c8ae,0xc99c4bed,
0x4bffc942,0xc7834be8,0x35b2ca08,0x4b10c0de,0xbc77c985,0x4bd7c6d4,0xcbfb49ca,0x425dcb3c,0xcbe54a46,0xbda3c9f7,0x412848f7,0xcbf84955,
0x4beec8fe,0xc80e4bf8,0xc02fca40,0x4ae53d8a,0xc89fc668,0x4be9c87b,0xca884b55,0xc0c5caa1,0xc7404bfb,0xc9e8c4a8,0x4b22bca9,0xc9654ba7,
0x4c00c83c,0xbb8e4b69,0xb376caca,0x4bfcc605,0xc5e2c9ff,0x4bad38cf,0xcb70494b,0x4484cbff,0xc4fc4bff,0xc9abc813,0x4b9ab7a8,0xc9a54ae2,
0x4ac6ca4e,0x44964add,0xc841c8ed,0x4baac81c,0xcbee42cc,0x428ecbfe,0xc03c4bd1,0xcbd53966,0xca804995,0x3934cc00,0x48a949bb,0xcbfe31e4,
0x4b97c745,0xc09f4bf7,0xc50ecb20,0x4beb3dee,0xcc004172,0x43e5cbd8,0x354d4be2,0xcbc1c244,0x4bb04023,0xc58a4ba4,0x446ccbef,0x4b8144c0,
0x4a1a4973,0xcbd53bc0,0x492dc9db,0x42824bfc,0xca8dc8e3,0x4b0cc579,0xc8974a55,0xc793cb85,0x4af24849,0xc9ae48c3,0x47f1cac1,0x49a34a6e,
0xcb48c74b,0x47afca65,0xc6a14b1f,0xcb04c8cf,0x4713ca1e,0x46f64bf4,0xcb2dc928,0x4b34bf01,0x36df4bd1,0xcb3dc9a0,0x4bff42d8,0xc6cf49b0,
0xc7d5cbb6,0x4bc53e52,0xcafa4441,0xc3a8cbf6,0x4ab749d5,0xc8d44866,0x4859c97a,0x4a614aaf,0xcbd2c8d9,0x4a24c10f,0xc2bf4a5d,0xc921cbe6,
0x4a4cc32e,0x42514b8c,0xc8f0cbcc,0x4bd8454f,0xb7444b25,0xcba6c9ef,0x4bff4734,0xc4b4495e,0xca01cb56,0x49b7c390,0xc9494662,0xc99acbc6,
0x38394a98,0xca77cbd4,0x4bff4888,0xc8b6429b,0xcbb7ca48,0x495cbe9d,0xc43b48f5,0xc9f1cbf5,0x484ec5bf,0x495a4c00,0xcabecb77,0x49f32248,
0x492a4bfb,0xca79beb6,0x4a1cbc44,0x48b44bf5,0x4bb14834,0xc5ff4411,0xc466cacf,0x4b6b4bbd,0x45cb4b2a,0xcbf7cad7,0x4b75471e,0xbe204826,
0xcb29c5c5,0xc21fc9ec,0x47244b76,0xcbdac961,0xc836cbb2,0x4b1846f1,0xcacdc460,0xc767cb35,0xc800cb01,0x4bec4ba1,0xcaedc7ba,0x406ec4d2,
0x484434e9,0x48214aad,0xcac5cc00,0x4ada4869,0x4bfa4b26,0xc5733e39,0x3cf4c72f,0x4b864bf6,0x46564a82,0xcb8fc9b2,0x4b5848a7,0x453d499e,
0xc9bfc707,0xbecfc590,0x49914b30,0xcbf4cb80,0xcbfacb4c,0x46174086,0x3cdb4690,0xcb66cbeb,0xca86cbb5,0x4a3448c5,0xc8a2c447,0xc90dca6c,
0xc41dc890,0x4bdd4b41,0xcbbbca93,0xc1eec6be,0x4acb4b5a,0xcb82cb5b,0x48394651,0x4584464b,0x493d4a16,0xcbc1cba5,0x4a0c4931,0x43d944ba,
0x466d4846,0xcbebcbd9,0x4b534ac3,0x40934238,0x3f334429,0xcbfecbf7,0x4bf34bba,0x39013dd5,0x4bfd4c00,0xc1bdb89d,0xbb5cb1e4,0xcbdfcbff,
0x4be94bf5,0xc73ac51a,0xc0c5be9d,0xcb23cb95,0x4bc54bd9,0xc97ec89a,0xc3a8c238,0xc9d1ca8b,0x4b8f4bac,0xcaecca46,0xc53dc48a,0xc803c8f7,
0xcba3cbfc,0x469b3d71,0x44c63bc0,0x4b494bf9,0xc9a5cad7,0x4b27498c,0x49ab4826,0x472949c4,0xc4b4c81e,0x4bd04bf0,0x4ba64adc,0xc2e43fe2,
0x41eebb2a,0x48fc4aca,0x4bdd4bfd,0xca42c83c,0x4ad44bf4,0xc8fac048,0xc82cbf01,0xca44cbee,0x409f4869,0xcbe1cb7b,0xcbebcaad,0x418bc5ae,
0xc95ac4a2,0xc514ca10,0xc9f3cba8,0x4b964939,0xcbfecb5f,0x497542cc,0x3901c63a,0x49d94bd1,0xc99ccbe6,0x4a5941d5,0x49b4410f,0x48de4bde,
0x4793c086,0x49814bfa,0x4b0c4beb,0xc9cfbd0d,0x4bda4b3b,0xc934367b,0xc21f46da,0xca14cbff,0x3ee8496a,0xca96cbef,0xcbf4c9e4,0x488bc023,
0x480e4bd4,0xcb57c35f,0xcae5c29b,0xc65ccbc9,0xcb3dc4ba,0xbfb0caf0,0xc6cfcba5,0x4bf147f6,0xc573cb65,0x4be349ca,0x4b86461d,0xc15a4985,
0x4bbe4772,0xc70d474b,0x440b4b15,0xcb2ecb1f,0xc484cbbd,0x4be54472,0x4bad4411,0x41344baf,0x4bd84967,0xc7eb4892,0xc25149e6,0xcaf4ca91,
0xc90d4567,0xc5d1cbfb,0xca34cb88,0x4b743ca9,0xc645cbec,0x4b9f497a,0x4b5c407a,0xc4de49d5,0x39344ba1,0xcbf9c531,0xcbfec4d2,0x3d3fcb91,
0xc95ccb68,0x4b52c14d,0x49f1c60b,0x46734be4,0x4beb4788,0xc8e648ed,0xc0934b0f,0xca53ca4e,0xcad24276,0x4128cb56,0xc82ecbd6,0x4be54662,
0x4282cb80,0x4b9345ee,0x4bd54590,0xc5264b6e,0x3e204bfd,0xcbcdc45a,0xcbf7baf8,0x4315cbb3,0xc62ecbc2,0x4bf24172,0x4b61c3cd,0xbf974be2,
0x49234ad5,0xcc00bc44,0xca224829,0x3376cbfb,0xc6f64b5b,0xcab9c6a7,0xcb34c64b,0x4856cb47,0x4821cb09,0x49364942,0x4ada479e,0xca124a08,
0xc8be4aa8,0xc68acac1,0xca72c871,0x4b4dc849,0x4950ca38,0x403c4bb2,0x49fb4908,0xcbee4460,0x4921cb31,0x4978475c,0x4a244702,0xc9d74b1b,
0xcb6648bb,0xbc90cb55,0xc617ca73,0x4bfbc668,0x4bf7c0b8,0xc8954bb6,0xbe074bea,0xca8fc441,0xcab2c549,0x4bb0c8a7,0x4861cb8d,0x446c4a82,
0xca774b03,0xc7c5c806,0xc8b6c7b4,0x4afecaea,0x4bc1c213,0xc84c4bff,0xc3d94bdb,0xcac0b7a8,0xc6e5c912,0x4bfbc734,0x4b38ca30,0xbc774b25,
0xc6b24c00,0xc6a1c890,0xcb442f12,0x4b48ca93,0x4b6bcad0,0x4423485c,0x45ff4831,0xcbba4ab6,0xc910c3f1,0x4b78cb20,0x4a32cbc0,0x45b94745,
0xc86b4bfd,0xc740c5bf,0xcaab3a61,0x4b22cb77,0x4baec57e,0xcab74bba,0xc47e4b83,0xc859c429,0xcbec4a9a,0xb420c8ae,0xc06ec885,0x4c00ca7d,
0x39fd491c,0xcbb548e3,0xcbfe4a28,0x444eca55,0x4bfec9a9,0xc8414b76,0xb9ca49a7,0xcac645c5,0x4061ca26,0x4949bd26,0x4bedc91e,0xca014bf9,
0x4bf4ca5f,0xc34648fe,0xbecf48d7,0xcbca4a40,0x4876cb40,0x48e8c2d8,0x4aa4c6c3,0xca514bd1,0xc799ba2f,0x4c00cb26,0x4b0acbfe,0xb54d472f,
0xcc004ae4,0x492acb4b,0xb11bc811,0x4a1cc696,0xcb824a20,0x4750c94b,0x4584c925,0x4b1dc9ff,0xcb8a4c00,0xb5b2c32e,0xc55bad7f,0x4bffcbcc,
0xc8164a2e,0xc7f14447,0xcae14914,0x4af2cbb5,0x41034207,0xcacd498e,0xcbe74bdb,0x4836c9c1,0x4a9dc9de,0xc9474995,0xc8804971,0xca0349bb,
0x4ba6cb37,0xc89f48f5,0xc4ae46eb,0xca884a48,0x4c00cbea,0xc7d54846,0x2bdb40ac,0xcafa4ac3,0x4ba2cbe8,0xc6564718,0x44ccc0ea,0xcb584b2c,
0xc9534997,0x4a94c9db,0x49f9c9b9,0x488dc973,0xc8c0490b,0x4b9acb2a,0x4a70ca36,0x44fcc71e,0xc8244873,0x4bffcbe2,0x4ad9caa6,0x3744c17f,
0xc6fc47a4,0x4bbbcbf2,0x4b33cb07,0xc41d3f65,0x476cc94e,0xcb7d4a1e,0xcb1649fd,0xc5a24928,0xa8b6c39c,0xcb974c00,0xcc004bc5,0x450e34e9,
0xc77d43c0,0xc84e4a4f,0xcb124bc3,0x4abec8eb,0xca9b4955,0x3f33433a,0xc88349f7,0x4bf3cbcb,0xc3834901,0x4bf3ca5d,0x4bc7ca3e,0x3f4cc8d9,
0x48c8c269,0x4897cb4c,0x4a6acbd6,0xca8d4690,0x4bfdcb0d,0xc724bcc2,0x3ac5c78e,0xcb294bfa,0x496ecb69,0xcbff4abb,0xc9e04605,0xb86b4854,
0xb052c8b1,0xcbee4a98,0xcc004a7b,0x402f4888,0xcba948cd,0x36df4931,0xc49c4a66,0x4bffca16,0xc8784b89,0x4bfac983,0x4aa2c561,0x3cf4c9cc,
0x4903b966,0x41c9ca57,0x4a3ccbfe,0xcbde48e1,0x4405485e,0x4b70cacf,0x4bbecab4,0xc5e2c834,0x4b87cb13,0xc8f0c42f,0xc56dc777,0xca4c4bb9,
0xc6c9c622,0xc8a24bff,0xcb3f4b64,0x4a86b616,0xcae74ba4,0x4b92c4ea,0x480b44c0,0x452ccb9d,0xc7a9c809,0xca804b01,0xcb064ae9,0x48a947ba,
0xc86e4bfe,0x4bb7c1a4,0x4aa93998,0x443bcbe0,0x4bf5c6d4,0xc66dc93b,0x3e84cb3c,0xcb534a0e,0xc5fac8cf,0xc7564bff,0xcb6c4a65,0x4b1c3806,
0x496c4761,0x492dcb30,0x49e2cb19,0xca1ac707,0xba93cb60,0xcb7548a4,0xcbfd4634,0x45cb4a84,0xc8ca4ba7,0x4bf0bfc9,0x4a6844a8,0x400acbf1,
0x4bc7c866,0xca7fc5dc,0xc377caaf,0xc8ac4b72,0xcab0c6ad,0xc7134b5a,0xc8634b45,0x4b2d4651,0x49174957,0x4844cafb,0x4a2cc9f5,0xcac5c7d0,
0xc611cadd,0xc8f24a8a,0xcb67481c,0x4a4a489d,0x3da34bc6,0x4993ca05,0x4bf8c390,0xc9bdc944,0x4b8e45f4,0x42bfcb7f,0x4543cb6d,0xcbd2c596,
0xcbc4c490,0x3cdb4bfb,0xc3b44bab,0x4bfa3c5e,0x4be94244,0xc5b3cbcf,0x40d1cbd8,0xcb7a42fd,0xcbfcbeb6,0x48dc4afd,0xbb8e4bf5,0x4a5bc7ca,
0xcbf8c537,0x38394ba0,0xbdbc4b90,0x4bff44d8,0x4b62c0de,0xc93dcb73,0xc628cbe8,0xca0c45d7,0xc91948c3,0x4be047e6,0x4a2a4a6e,0x4197caf5,
0x428ecb35,0xcb004141,0xcbd5c6f1,0x47bf4be4,0x4be74478,0xc466cbbc,0xc0f6cbaf,0xcbb1c417,0xc819487b,0x4bcf497c,0x4adf4aa1,0x42f0c9d3,
0xc555cbf6,0xc9404502,0xcb8bbe52,0x4a0a4b99,0x4b8149b2,0xc59ccbdf,0x458ac99e,0xcb7ec1b0,0xcb5dc36b,0x48004bd3,0x463f4bc8,0x4aed42a7,
0xbe6bcae2,0xcb4ec4f0,0xcbf6c813,0x46844b9c,0x4bd749ef,0xc4f6cb50,0x425dc95e,0xcb9bc67f,0xc7af46be,0x4bd347fb,0x4b044b41,0xc2b3caef,
0x4a6341e2,0xc991cbe6,0xc8d2cbdd,0xc9bfc11c,0x49634bf7,0x47dbc016,0x49ea3dee,0xcaf8cbef,0xc965a248,0x4bcd4b51,0x49e84c00,0x4322c679,
0xca61cbf7,0x3c12492f,0xc8d43dd5,0x4bfc4a18,0xc906c055,0x4acb4bf3,0x4a3a4bed,0x48393f1a,0xcbdacb85,0x3ffb4851,0xc22c4579,0x4bf04abc,
0xc496c9ec,0xc98ac508,0xcbaac961,0x49c64b98,0x49b743fd,0xcbf9cb7c,0xc99acbbf,0xbd5845a8,0x46b83d8a,0xcb9ecbfc,0xcb43cbf8,0xc4e4bbf2,
0x4b3949a0,0xc988cac8,0xc6e0c9b0,0xc9c8c83e,0x4bc14bf6,0xc435c7e0,0x43e5be39,0xcbb8caf7,0x48b44a9f,0x4352b484,0x4a79487e,0xcbcacc00,
0xc1fab8cf,0x4bfc4c00,0x4bdc4bff,0x3c2b32ad,0xc783c54f,0x4be34bf2,0x4b104b8c,0x41663f7e,0xc9aec8c5,0x4bb44bce,0x49a34a6c,0x44544309,
0xcb18ca75,0x4b6f4b94,0x476748b9,0x45e84520,0x4bfd4c00,0x41bd389d,0xbb5cb1e4,0x4bdf4bff,0x4be94bf5,0x473a451a,0xc0c5be9d,0x4b234b95,
0x4bc54bd9,0x497e489a,0xc3a8c238,0x49d14a8b,0x4b8f4bac,0x4aec4a46,0xc53dc48a,0x480348f7,0xcba3cbfc,0xc69bbd71,0x44c63bc0,0xcb49cbf9,
0xc9a5cad7,0xcb27c98c,0x49ab4826,0xc729c9c4,0xc4b4c81e,0xcbd0cbf0,0x4ba64adc,0x42e4bfe2,0x41eebb2a,0xc8fccaca,0x4bdd4bfd,0x4a42483c,
0x4ad44bf4,0x48fa4048,0xc82cbf01,0x4a444bee,0x409f4869,0x4be14b7b,0xcbebcaad,0xc18b45ae,0xc95ac4a2,0x45144a10,0xc9f3cba8,0xcb96c939,
0xcbfecb5f,0xc975c2cc,0x3901c63a,0xc9d9cbd1,0xc99ccbe6,0xca59c1d5,0x49b4410f,0xc8decbde,0x4793c086,0xc981cbfa,0x4b0c4beb,0x49cf3d0d,
0x4bda4b3b,0x4934b67b,0xc21f46da,0x4a144bff,0x3ee8496a,0x4a964bef,0xcbf4c9e4,0xc88b4023,0x480e4bd4,0x4b57435f,0xcae5c29b,0x465c4bc9,
0xcb3dc4ba,0x3fb04af0,0xc6cfcba5,0xcbf1c7f6,0xc573cb65,0xcbe3c9ca,0x4b86461d,0x415ac985,0x4bbe4772,0x470dc74b,0x440b4b15,0x4b2e4b1f,
0xc484cbbd,0xcbe5c472,0x4bad4411,0xc134cbaf,0x4bd84967,0x47ebc892,0xc25149e6,0x4af44a91,0xc90d4567,0x45d14bfb,0xca34cb88,0xcb74bca9,
0xc645cbec,0xcb9fc97a,0x4b5c407a,0x44dec9d5,0x39344ba1,0x4bf94531,0xcbfec4d2,0xbd3f4b91,0xc95ccb68,0xcb52414d,0x49f1c60b,0xc673cbe4,
0x4beb4788,0x48e6c8ed,0xc0934b0f,0x4a534a4e,0xcad24276,0xc1284b56,0xc82ecbd6,0xcbe5c662,0x4282cb80,0xcb93c5ee,0x4bd54590,0x4526cb6e,
0x3e204bfd,0x4bcd445a,0xcbf7baf8,0xc3154bb3,0xc62ecbc2,0xcbf2c172,0x4b61c3cd,0x3f97cbe2,0x49234ad5,0x4c003c44,0xca224829,0xb3764bfb,
0xc6f64b5b,0x4ab946a7,0xcb34c64b,0xc8564b47,0x4821cb09,0xc936c942,0x4ada479e,0x4a12ca08,0xc8be4aa8,0x468a4ac1,0xca72c871,0xcb4d4849,
0x4950ca38,0xc03ccbb2,0x49fb4908,0x4beec460,0x4921cb31,0xc978c75c,0x4a244702,0x49d7cb1b,0xcb6648bb,0x3c904b55,0xc617ca73,0xcbfb4668,
0x4bf7c0b8,0x4895cbb6,0xbe074bea,0x4a8f4441,0xcab2c549,0xcbb048a7,0x4861cb8d,0xc46cca82,0xca774b03,0x47c54806,0xc8b6c7b4,0xcafe4aea,
0x4bc1c213,0x484ccbff,0xc3d94bdb,0x4ac037a8,0xc6e5c912,0xcbfb4734,0x4b38ca30,0x3c77cb25,0xc6b24c00,0x46a14890,0xcb442f12,0xcb484a93,
0x4b6bcad0,0xc423c85c,0x45ff4831,0x4bbacab6,0xc910c3f1,0xcb784b20,0x4a32cbc0,0xc5b9c745,0xc86b4bfd,0x474045bf,0xcaab3a61,0xcb224b77,
0x4baec57e,0x4ab7cbba,0xc47e4b83,0x48594429,0xcbec4a9a,0x342048ae,0xc06ec885,0xcc004a7d,0x39fd491c,0x4bb5c8e3,0xcbfe4a28,0xc44e4a55,
0x4bfec9a9,0x4841cb76,0xb9ca49a7,0x4ac6c5c5,0x4061ca26,0xc9493d26,0x4bedc91e,0x4a01cbf9,0x4bf4ca5f,0x4346c8fe,0xbecf48d7,0x4bcaca40,
0x4876cb40,0xc8e842d8,0x4aa4c6c3,0x4a51cbd1,0xc799ba2f,0xcc004b26,0x4b0acbfe,0x354dc72f,0xcc004ae4,0xc92a4b4b,0xb11bc811,0xca1c4696,
0xcb824a20,0xc750494b,0x4584c925,0xcb1d49ff,0xcb8a4c00,0x35b2432e,0xc55bad7f,0xcbff4bcc,0xc8164a2e,0x47f1c447,0xcae14914,0xcaf24bb5,
0x41034207,0x4acdc98e,0xcbe74bdb,0xc83649c1,0x4a9dc9de,0x4947c995,0xc8804971,0x4a03c9bb,0x4ba6cb37,0x489fc8f5,0xc4ae46eb,0x4a88ca48,
0x4c00cbea,0x47d5c846,0x2bdb40ac,0x4afacac3,0x4ba2cbe8,0x4656c718,0x44ccc0ea,0x4b58cb2c,0xc9534997,0xca9449db,0x49f9c9b9,0xc88d4973,
0xc8c0490b,0xcb9a4b2a,0x4a70ca36,0xc4fc471e,0xc8244873,0xcbff4be2,0x4ad9caa6,0xb744417f,0xc6fc47a4,0xcbbb4bf2,0x4b33cb07,0x441dbf65,
0x476cc94e,0x4b7dca1e,0xcb1649fd,0x45a2c928,0xa8b6c39c,0x4b97cc00,0xcc004bc5,0xc50eb4e9,0xc77d43c0,0x484eca4f,0xcb124bc3,0xcabe48eb,
0xca9b4955,0xbf33c33a,0xc88349f7,0xcbf34bcb,0xc3834901,0xcbf34a5d,0x4bc7ca3e,0xbf4c48d9,0x48c8c269,0xc8974b4c,0x4a6acbd6,0x4a8dc690,
0x4bfdcb0d,0x47243cc2,0x3ac5c78e,0x4b29cbfa,0x496ecb69,0x4bffcabb,0xc9e04605,0x386bc854,0xb052c8b1,0x4beeca98,0xcc004a7b,0xc02fc888,
0xcba948cd,0xb6dfc931,0xc49c4a66,0xcbff4a16,0xc8784b89,0xcbfa4983,0x4aa2c561,0xbcf449cc,0x4903b966,0xc1c94a57,0x4a3ccbfe,0x4bdec8e1,
0x4405485e,0xcb704acf,0x4bbecab4,0x45e24834,0x4b87cb13,0x48f0442f,0xc56dc777,0x4a4ccbb9,0xc6c9c622,0x48a2cbff,0xcb3f4b64,0xca863616,
0xcae74ba4,0xcb9244ea,0x480b44c0,0xc52c4b9d,0xc7a9c809,0x4a80cb01,0xcb064ae9,0xc8a9c7ba,0xc86e4bfe,0xcbb741a4,0x4aa93998,0xc43b4be0,
0x4bf5c6d4,0x466d493b,0x3e84cb3c,0x4b53ca0e,0xc5fac8cf,0x4756cbff,0xcb6c4a65,0xcb1cb806,0x496c4761,0xc92d4b30,0x49e2cb19,0x4a1a4707,
0xba93cb60,0x4b75c8a4,0xcbfd4634,0xc5cbca84,0xc8ca4ba7,0xcbf03fc9,0x4a6844a8,0xc00a4bf1,0x4bc7c866,0x4a7f45dc,0xc377caaf,0x48accb72,
0xcab0c6ad,0x4713cb5a,0xc8634b45,0xcb2dc651,0x49174957,0xc8444afb,0x4a2cc9f5,0x4ac547d0,0xc611cadd,0x48f2ca8a,0xcb67481c,0xca4ac89d,
0x3da34bc6,0xc9934a05,0x4bf8c390,0x49bd4944,0x4b8e45f4,0xc2bf4b7f,0x4543cb6d,0x4bd24596,0xcbc4c490,0xbcdbcbfb,0xc3b44bab,0xcbfabc5e,
0x4be94244,0x45b34bcf,0x40d1cbd8,0x4b7ac2fd,0xcbfcbeb6,0xc8dccafd,0xbb8e4bf5,0xca5b47ca,0xcbf8c537,0xb839cba0,0xbdbc4b90,0xcbffc4d8,
0x4b62c0de,0x493d4b73,0xc628cbe8,0x4a0cc5d7,0xc91948c3,0xcbe0c7e6,0x4a2a4a6e,0xc1974af5,0x428ecb35,0x4b00c141,0xcbd5c6f1,0xc7bfcbe4,
0x4be74478,0x44664bbc,0xc0f6cbaf,0x4bb14417,0xc819487b,0xcbcfc97c,0x4adf4aa1,0xc2f049d3,0xc555cbf6,0x4940c502,0xcb8bbe52,0xca0acb99,
0x4b8149b2,0x459c4bdf,0x458ac99e,0x4b7e41b0,0xcb5dc36b,0xc800cbd3,0x463f4bc8,0xcaedc2a7,0xbe6bcae2,0x4b4e44f0,0xcbf6c813,0xc684cb9c,
0x4bd749ef,0x44f64b50,0x425dc95e,0x4b9b467f,0xc7af46be,0xcbd3c7fb,0x4b044b41,0x42b34aef,0x4a6341e2,0x49914be6,0xc8d2cbdd,0x49bf411c,
0x49634bf7,0xc7db4016,0x49ea3dee,0x4af84bef,0xc965a248,0xcbcdcb51,0x49e84c00,0xc3224679,0xca61cbf7,0xbc12c92f,0xc8d43dd5,0xcbfcca18,
0xc906c055,0xcacbcbf3,0x4a3a4bed,0xc839bf1a,0xcbdacb85,0xbffbc851,0xc22c4579,0xcbf0cabc,0xc496c9ec,0x498a4508,0xcbaac961,0xc9c6cb98,
0x49b743fd,0x4bf94b7c,0xc99acbbf,0x3d58c5a8,0x46b83d8a,0x4b9e4bfc,0xcb43cbf8,0x44e43bf2,0x4b3949a0,0x49884ac8,0xc6e0c9b0,0x49c8483e,
0x4bc14bf6,0x443547e0,0x43e5be39,0x4bb84af7,0x48b44a9f,0xc3523484,0x4a79487e,0x4bca4c00,0xc1fab8cf,0xcbfccc00,0x4bdc4bff,0xbc2bb2ad,
0xc783c54f,0xcbe3cbf2,0x4b104b8c,0xc166bf7e,0xc9aec8c5,0xcbb4cbce,0x49a34a6c,0xc454c309,0xcb18ca75,0xcb6fcb94,0x476748b9,0xc5e8c520,
0x4b494b6e,0xcbc7cb6d,0xc69bc5ee,0xc383c5f4,0x4af44b20,0xcbfdcbf7,0xc7ebc745,0x3a93bdee,0x4a8f4ac3,0xcb8bcbd9,0xc895c846,0x45554238,
0x4a1c4a57,0xca79cb15,0xc92ac8e1,0x48b44772,0x48fa46a7,0xb0524537,0x4a444b47,0xcc00cb90,0x4b524a55,0xc917c579,0x467348e3,0xca2ccb85,
0x4bfb4be2,0xcbd7cadc,0xbc77417f,0xc25dc81e,0x4acd4b9d,0xcb18cbec,0xc836c4ea,0x4767407a,0xc8decb1b,0x4bbe4baf,0x4a59475c,0xc4054478,
0x4315c2d8,0x43b449a0,0x4bcd4bd1,0xcbc4c9b0,0x4b2248eb,0xc9e8c4a2,0x47404a4f,0xc965cba8,0x4b584bff,0xcb8fcbd6,0xc6563806,0x453dc276,
0xcb57c806,0x47a9c36b,0xc65ccaea,0x4b064bc8,0xc936cbcc,0x4b624b8c,0x4a12432e,0xc628454f,0x4841bcc2,0xc49646da,0x4ac64bfa,0xcbaacb3b,
0x4bbb4b72,0xcbddcad5,0xc41d45dc,0x41eec829,0x41344ab6,0xc9e2cbdd,0xcbe5c85c,0x496cc1e2,0xcbfbc8f5,0x4adf3e9d,0xbc90ca48,0x48194bf5,
0x354dc9cc,0x43e54b65,0x4c004983,0xcbc1c61d,0x4bf34a05,0xcbfec908,0xbf334944,0x3901ca38,0x4bf948ae,0xcab04055,0xbd3f4a7d,0xc863cbed,
0xc84c471e,0x3e6bcad7,0xcac0cb2a,0x4bf64826,0xc7f1cbff,0x49ae4b88,0x4af23616,0xc9a34567,0x4bff47ca,0xcbf4c549,0x386b4afd,0xbee8cb8d,
0x4526ca40,0x45434bf8,0x4b9348fe,0xcb8e3d8a,0x45b94c00,0xc9eacaad,0xcb7834e9,0x4963c869,0xcafaca0e,0x4bc54788,0x47d5c93b,0xc3a84b0f,
0x4bde4141,0xcbbe2f12,0x41c94be4,0xc40bcc00,0xcab9c94b,0x4bf8b8cf,0x4856c9ff,0x3dbc4bff,0x4bb54690,0xcbda4086,0xc44e4b4c,0xc22ccbeb,
0xcbffbfc9,0x4ba6c3cd,0xb744cbf1,0x44b44bc2,0x4b92c1b0,0xcb5c457e,0x452c4bdf,0xc645cb83,0xc9d749bb,0x40f6cc00,0xc978c995,0x4be731e4,
0x4a51c931,0xc6e04ba5,0x48e84a16,0xcb39c4ba,0xcabe489d,0x495acaa8,0xc84eca8a,0x49f34871,0x4b1cc7fb,0xcad2491e,0x47564aef,0xc82eca26,
0x47c549db,0xcb5dbbc0,0xcafe4973,0x463fcbfc,0xb5b2cbb9,0x47834967,0x4bffc42f,0xcb1049e6,0xc7244bcf,0x421fcbea,0xcb29c2fd,0x4bdac0b8,
0x4a7fca18,0xca224ae4,0x48ac492f,0xc923c811,0x4bbac928,0xc8d24bf4,0x44234a1e,0xca63bf01,0xca88c1a4,0x4be9c60b,0x489fcbe0,0xc0c54b68,
0x3cf44af5,0xc573c912,0xcbfa47e6,0x4b86ca30,0x49bdcb7c,0xc9504bdb,0x499345a8,0xc9fbc207,0xb420ca5d,0x4906410f,0x4c00c8d9,0xca3a4be6,
0xcb9a4a84,0x49abcbfd,0xc4fcc8a4,0x49a53af8,0x48a24502,0xca343a61,0xca864b99,0x490dcbfd,0x48dccc00,0xc8614be8,0x4a5b3484,0xcab240ea,
0xcbca4888,0x4b43cbd4,0x4346ca98,0x46b8429b,0xc50e4afb,0xc09fc79e,0xcb9747d0,0x4bebcb09,0x4b53c67f,0xcbeb49a9,0xc66d4b50,0x4093c9a7,
0x47bfcb94,0xc6b24b07,0x4b00c520,0xcb4447a4,0xc7504acf,0xc1fac411,0xcb1d4834,0x4bdccbbd,0x4897bc5e,0xcb0c48bb,0xca8d4bfb,0x4793ca73,
0x4bf0cb51,0xcb614bfe,0x400a4679,0xc62eba2f,0x459cca46,0xc47e4955,0x4b7ec8f7,0xcbae49f7,0x4a03c7ba,0xcbfd4ba1,0xc9474b01,0x3b5cc4d2,
0x4bffcb73,0xcb3d4bdb,0xb6df45d7,0xc6cf4213,0x4a4acb98,0xc8be4a2e,0x48f2c508,0xca724914,0x42b3c83c,0xc0614605,0x4bd3caca,0xcbed4b69,
0x4a94cb30,0xc4c64590,0x488dc707,0xcba34b80,0x48f0c9d3,0xc25143f1,0x4a4cc97c,0xcbd84bc0,0x45b3c7e0,0xbe0740ac,0x4b7acaf7,0xcbf74bea,
0x3c12c2cc,0x311b3966,0x4bfccbd1,0xcc004bfe,0xc5a24651,0x4ad4cb5b,0x4b7dcb5a,0xc82c464b,0xc43b44f0,0x495cca28,0x4bb7cb9c,0xc9f1491c,
0xc1974309,0x46e5c873,0x4be0cbce,0xcb384aa6,0xbd584023,0x4103c4c0,0x4bf9cbef,0xcbe74ba4,0xcbf34b7f,0x49b4c702,0xbf4c4596,0x499ccb31,
0xcb754bef,0x4bf7cb40,0x45cbc016,0x3e20c6c3,0xc9404a8b,0x4aabcbc3,0x4a0ac89a,0xc86b43c0,0xc352474b,0x44ccc8cf,0x4bcacb1f,0xcba24a65,
0xc02fc4d8,0xc80e4b03,0xcbee4ba0,0x4ae5c7b4,0xcac54851,0x4821ad7f,0xc8444abc,0x4adacc00,0xcb9b4bf0,0x4bfecb0d,0x44f63fe2,0xb9cac78e,
0xc5e849d5,0x46fccaaf,0x4b6fc97a,0xcb334866,0x4b70cbbc,0xcbad4831,0xc5e2c417,0xc4844ad0,0xbcdbc83e,0xc6174b37,0xcbfa4ac8,0x4b66c6eb,
0xcbcd4939,0x4b0ac561,0xc3224a10,0x4799cb89,0xc8034b56,0x4883cbc6,0x4aecc662,0xca9b4390,0x48a942a7,0x3934ca9a,0x4a80cbd3,0xcbfe4885,
0x4a0ccbf2,0xcbc14a36,0xc93dbf7e,0x43d9490b,0xc9c6b67b,0x48164622,0xc98a4bff,0x4ae1cb64,0xc8fc4bfb,0x496ecbf5,0x4a42bc44,0xc9e0beb6,
0xc92d4be6,0x4bd5c8d7,0x4a1a411c,0xc282ca5f,0x4bcfc51a,0xca32c39c,0x42f0cb95,0xc9104bc5,0xc435c985,0xabdb4b3c,0xcbb849ca,0x4c00c6d4,
0xc9d94bb2,0x4a3ccb35,0x49754460,0xc903c6f1,0xcb2dbf1a,0x46f64a20,0xc7134bf3,0x4b34c925,0x468449c4,0x39fdcbd6,0x4b4ec98c,0xcbfe4269,
0x4454cbfb,0xc8244ba7,0xcbb43ca9,0x4ad944a8,0xca964a82,0x4ae7c99e,0x488b48a7,0xc80bc9b2,0x42bfcbfc,0xca244971,0xcbd2bbf2,0x492149de,
0xc7db4b7b,0x4aa4c8cd,0x4af845ae,0xc876ca66,0x49d1ca4e,0xcb12481c,0xc97ec8ed,0x477d4add,0xcb2e4890,0x4b6cc6be,0x470d4a93,0xc5facb41,
0x4bff32ad,0xca77c997,0xb839cc00,0xc8b649b9,0xcbf03d0d,0x4b8a4777,0x3ffb4bfa,0x455bcb13,0x4bd0c172,0xcbfdc244,0xc2e4cbe2,0xbac54bd8,
0xcb9f4429,0x4bc7bdd5,0x44de4bba,0xc377cbf7,0x44664bff,0x45ffc9fd,0x4bb1b89d,0xcb6bc94e,0xc988caf0,0x44ae4bfe,0xc9c847f6,0x4ba63998,
0x4b964849,0xcaa2ca6e,0x4514cac1,0xc87848c3,0xcbe5bd26,0x4bf843fd,0x41284bf9,0xbda3cbbf,0xcaed3d71,0x4bec4901,0x48004bf9,0x406eca3e,
0x4166ca91,0xc8c04634,0xcbe3c892,0x4a704b60,0x49344bb6,0xc6c9cbf6,0x4a14c441,0xcb3fbe52,0xcc00c696,0x4bfc487e,0x33764b4b,0x3b8eca9f,
0xc991cbee,0x3ecf4a7b,0xc9bf4048,0x4bf448b1,0x4b23414d,0xcc00c957,0xc73acbe4,0x28b649f5,0x415a4b25,0x3e84c95e,0x4be34734,0xcbf5c9ef,
0xcbeec98e,0x4bd54a75,0xc03c49c1,0x428ec8b9,0x4839c1d5,0xcb82c85e,0xcacbcbde,0x45844ab4,0x4b274bb3,0xc8c8cbab,0x4729c45a,0xca6ac490,
0xc5d145bf,0x48ca2248,0x4b744b77,0xca68cc00,0xcbb0cb2c,0x4b814bac,0xc46c4718,0x458ac48a,0x4b9e4bc9,0xc880cae9,0x44e4c35f,0xca9dc809,
0x418b4942,0x449cc0de,0x4be14a08,0xcba9cbe8,0xca53c5c5,0x4b674961,0x48e64b76,0xc611c9ec,0xcb48cbf2,0x4b044bfd,0xc6a13f65,0x47af3b2a,
0xbc2b4472,0x49534761,0x4bfc4baf,0xc9f9cb19,0xc981c668,0x4b874aa1,0x49cf4b55,0xc56dc87b,0xcbf2cb26,0x4be94bf6,0x3f97472f,0x40d1be39,
0xcab7cbcb,0x4a614b5f,0xc859c33a,0x48d4463a,0xcbdfcb91,0x4b164b45,0x41bd4531,0x476c46ad,0xcbf1cbff,0x4aa94ae2,0xbfb037a8,0x486e4813,
0xcb4dcbb5,0x4a2a4a6c,0xc68ac447,0x491948c5,0xca01cabb,0x499a49e4,0xc949c854,0x49b7496a,0x4b494b6e,0x4bc74b6d,0xc69bc5ee,0x438345f4,
0x4af44b20,0x4bfd4bf7,0xc7ebc745,0xba933dee,0x4a8f4ac3,0x4b8b4bd9,0xc895c846,0xc555c238,0x4a1c4a57,0x4a794b15,0xc92ac8e1,0xc8b4c772,
0x48fa46a7,0x3052c537,0x4a444b47,0x4c004b90,0x4b524a55,0x49174579,0x467348e3,0x4a2c4b85,0x4bfb4be2,0x4bd74adc,0xbc77417f,0x425d481e,
0x4acd4b9d,0x4b184bec,0xc836c4ea,0xc767c07a,0xc8decb1b,0xcbbecbaf,0x4a59475c,0x4405c478,0x4315c2d8,0xc3b4c9a0,0x4bcd4bd1,0x4bc449b0,
0x4b2248eb,0x49e844a2,0x47404a4f,0x49654ba8,0x4b584bff,0x4b8f4bd6,0xc6563806,0xc53d4276,0xcb57c806,0xc7a9436b,0xc65ccaea,0xcb06cbc8,
0xc936cbcc,0xcb62cb8c,0x4a12432e,0x4628c54f,0x4841bcc2,0x4496c6da,0x4ac64bfa,0x4baa4b3b,0x4bbb4b72,0x4bdd4ad5,0xc41d45dc,0xc1ee4829,
0x41344ab6,0x49e24bdd,0xcbe5c85c,0xc96c41e2,0xcbfbc8f5,0xcadfbe9d,0xbc90ca48,0xc819cbf5,0x354dc9cc,0xc3e5cb65,0x4c004983,0x4bc1461d,
0x4bf34a05,0x4bfe4908,0xbf334944,0xb9014a38,0x4bf948ae,0x4ab0c055,0xbd3f4a7d,0x48634bed,0xc84c471e,0xbe6b4ad7,0xcac0cb2a,0xcbf6c826,
0xc7f1cbff,0xc9aecb88,0x4af23616,0x49a3c567,0x4bff47ca,0x4bf44549,0x386b4afd,0x3ee84b8d,0x4526ca40,0xc543cbf8,0x4b9348fe,0x4b8ebd8a,
0x45b94c00,0x49ea4aad,0xcb7834e9,0xc9634869,0xcafaca0e,0xcbc5c788,0x47d5c93b,0x43a8cb0f,0x4bde4141,0x4bbeaf12,0x41c94be4,0x440b4c00,
0xcab9c94b,0xcbf838cf,0x4856c9ff,0xbdbccbff,0x4bb54690,0x4bdac086,0xc44e4b4c,0x422c4beb,0xcbffbfc9,0xcba643cd,0xb744cbf1,0xc4b4cbc2,
0x4b92c1b0,0x4b5cc57e,0x452c4bdf,0x46454b83,0xc9d749bb,0xc0f64c00,0xc978c995,0xcbe7b1e4,0x4a51c931,0x46e0cba5,0x48e84a16,0x4b3944ba,
0xcabe489d,0xc95a4aa8,0xc84eca8a,0xc9f3c871,0x4b1cc7fb,0x4ad2c91e,0x47564aef,0x482e4a26,0x47c549db,0x4b5d3bc0,0xcafe4973,0xc63f4bfc,
0xb5b2cbb9,0xc783c967,0x4bffc42f,0x4b10c9e6,0xc7244bcf,0xc21f4bea,0xcb29c2fd,0xcbda40b8,0x4a7fca18,0x4a22cae4,0x48ac492f,0x49234811,
0x4bbac928,0x48d2cbf4,0x44234a1e,0x4a633f01,0xca88c1a4,0xcbe9460b,0x489fcbe0,0x40c5cb68,0x3cf44af5,0x45734912,0xcbfa47e6,0xcb864a30,
0x49bdcb7c,0x4950cbdb,0x499345a8,0x49fb4207,0xb420ca5d,0xc906c10f,0x4c00c8d9,0x4a3acbe6,0xcb9a4a84,0xc9ab4bfd,0xc4fcc8a4,0xc9a5baf8,
0x48a24502,0x4a34ba61,0xca864b99,0xc90d4bfd,0x48dccc00,0x4861cbe8,0x4a5b3484,0x4ab2c0ea,0xcbca4888,0xcb434bd4,0x4346ca98,0xc6b8c29b,
0xc50e4afb,0x409f479e,0xcb9747d0,0xcbeb4b09,0x4b53c67f,0x4bebc9a9,0xc66d4b50,0xc09349a7,0x47bfcb94,0x46b2cb07,0x4b00c520,0x4b44c7a4,
0xc7504acf,0x41fa4411,0xcb1d4834,0xcbdc4bbd,0x4897bc5e,0x4b0cc8bb,0xca8d4bfb,0xc7934a73,0x4bf0cb51,0x4b61cbfe,0x400a4679,0x462e3a2f,
0x459cca46,0x447ec955,0x4b7ec8f7,0x4baec9f7,0x4a03c7ba,0x4bfdcba1,0xc9474b01,0xbb5c44d2,0x4bffcb73,0x4b3dcbdb,0xb6df45d7,0x46cfc213,
0x4a4acb98,0x48beca2e,0x48f2c508,0x4a72c914,0x42b3c83c,0x4061c605,0x4bd3caca,0x4bedcb69,0x4a94cb30,0x44c6c590,0x488dc707,0x4ba3cb80,
0x48f0c9d3,0x4251c3f1,0x4a4cc97c,0x4bd8cbc0,0x45b3c7e0,0x3e07c0ac,0x4b7acaf7,0x4bf7cbea,0x3c12c2cc,0xb11bb966,0x4bfccbd1,0x4c00cbfe,
0xc5a24651,0xcad44b5b,0x4b7dcb5a,0x482cc64b,0xc43b44f0,0xc95c4a28,0x4bb7cb9c,0x49f1c91c,0xc1974309,0xc6e54873,0x4be0cbce,0x4b38caa6,
0xbd584023,0xc10344c0,0x4bf9cbef,0x4be7cba4,0xcbf34b7f,0xc9b44702,0xbf4c4596,0xc99c4b31,0xcb754bef,0xcbf74b40,0x45cbc016,0xbe2046c3,
0xc9404a8b,0xcaab4bc3,0x4a0ac89a,0x486bc3c0,0xc352474b,0xc4cc48cf,0x4bcacb1f,0x4ba2ca65,0xc02fc4d8,0x480ecb03,0xcbee4ba0,0xcae547b4,
0xcac54851,0xc8212d7f,0xc8444abc,0xcada4c00,0xcb9b4bf0,0xcbfe4b0d,0x44f63fe2,0x39ca478e,0xc5e849d5,0xc6fc4aaf,0x4b6fc97a,0x4b33c866,
0x4b70cbbc,0x4badc831,0xc5e2c417,0x4484cad0,0xbcdbc83e,0x4617cb37,0xcbfa4ac8,0xcb6646eb,0xcbcd4939,0xcb0a4561,0xc3224a10,0xc7994b89,
0xc8034b56,0xc8834bc6,0x4aecc662,0x4a9bc390,0x48a942a7,0xb9344a9a,0x4a80cbd3,0x4bfec885,0x4a0ccbf2,0x4bc1ca36,0xc93dbf7e,0xc3d9c90b,
0xc9c6b67b,0xc816c622,0xc98a4bff,0xcae14b64,0xc8fc4bfb,0xc96e4bf5,0x4a42bc44,0x49e03eb6,0xc92d4be6,0xcbd548d7,0x4a1a411c,0x42824a5f,
0x4bcfc51a,0x4a32439c,0x42f0cb95,0x4910cbc5,0xc435c985,0x2bdbcb3c,0xcbb849ca,0xcc0046d4,0xc9d94bb2,0xca3c4b35,0x49754460,0x490346f1,
0xcb2dbf1a,0xc6f6ca20,0xc7134bf3,0xcb344925,0x468449c4,0xb9fd4bd6,0x4b4ec98c,0x4bfec269,0x4454cbfb,0x4824cba7,0xcbb43ca9,0xcad9c4a8,
0xca964a82,0xcae7499e,0x488b48a7,0x480b49b2,0x42bfcbfc,0x4a24c971,0xcbd2bbf2,0xc921c9de,0xc7db4b7b,0xcaa448cd,0x4af845ae,0x48764a66,
0x49d1ca4e,0x4b12c81c,0xc97ec8ed,0xc77dcadd,0xcb2e4890,0xcb6c46be,0x470d4a93,0x45fa4b41,0x4bff32ad,0x4a774997,0xb839cc00,0x48b6c9b9,
0xcbf03d0d,0xcb8ac777,0x3ffb4bfa,0xc55b4b13,0x4bd0c172,0x4bfd4244,0xc2e4cbe2,0x3ac5cbd8,0xcb9f4429,0xcbc73dd5,0x44de4bba,0x43774bf7,
0x44664bff,0xc5ff49fd,0x4bb1b89d,0x4b6b494e,0xc988caf0,0xc4aecbfe,0xc9c847f6,0xcba6b998,0x4b964849,0x4aa24a6e,0x4514cac1,0x4878c8c3,
0xcbe5bd26,0xcbf8c3fd,0x41284bf9,0x3da34bbf,0xcaed3d71,0xcbecc901,0x48004bf9,0xc06e4a3e,0x4166ca91,0x48c0c634,0xcbe3c892,0xca70cb60,
0x49344bb6,0x46c94bf6,0x4a14c441,0x4b3f3e52,0xcc00c696,0xcbfcc87e,0x33764b4b,0xbb8e4a9f,0xc991cbee,0xbecfca7b,0xc9bf4048,0xcbf4c8b1,
0x4b23414d,0x4c004957,0xc73acbe4,0xa8b6c9f5,0x415a4b25,0xbe84495e,0x4be34734,0x4bf549ef,0xcbeec98e,0xcbd5ca75,0xc03c49c1,0xc28e48b9,
0x4839c1d5,0x4b82485e,0xcacbcbde,0xc584cab4,0x4b274bb3,0x48c84bab,0x4729c45a,0x4a6a4490,0xc5d145bf,0xc8caa248,0x4b744b77,0x4a684c00,
0xcbb0cb2c,0xcb81cbac,0xc46c4718,0xc58a448a,0x4b9e4bc9,0x48804ae9,0x44e4c35f,0x4a9d4809,0x418b4942,0xc49c40de,0x4be14a08,0x4ba94be8,
0xca53c5c5,0xcb67c961,0x48e64b76,0x461149ec,0xcb48cbf2,0xcb04cbfd,0xc6a13f65,0xc7afbb2a,0xbc2b4472,0xc953c761,0x4bfc4baf,0x49f94b19,
0xc981c668,0xcb87caa1,0x49cf4b55,0x456d487b,0xcbf2cb26,0xcbe9cbf6,0x3f97472f,0xc0d13e39,0xcab7cbcb,0xca61cb5f,0xc859c33a,0xc8d4c63a,
0xcbdfcb91,0xcb16cb45,0x41bd4531,0xc76cc6ad,0xcbf1cbff,0xcaa9cae2,0xbfb037a8,0xc86ec813,0xcb4dcbb5,0xca2aca6c,0xc68ac447,0xc919c8c5,
0xca01cabb,0xc99ac9e4,0xc949c854,0xc9b7c96a,0x3cfa3d81,0xbbd0bb9c,0xb3e3b5a1,0x3bc53b8c,0x3c193c83,0xbbffbbf1,0xaa31b0ac,0x3bfe3beb,
0x3abf3b70,0xbbe3bbfb,0x30ac2a31,0x3beb3bfe,0x39853a1c,0xbb7bbbb8,0x35a133e3,0x3b8c3bc5,0x3c703cdd,0xbbf5bbda,0xb35eb53f,0x3bcc3b9a,
0x3b673c0d,0xbbfabc00,0xa9ccb05f,0x3bfe3bed,0x3a293ac2,0xbbbcbbe3,0x305f29cc,0x3bed3bfe,0x3914399a,0xbb3dbb85,0x353f335e,0x3b9a3bcc,
0x3bec3c4f,0xbc00bbfa,0xb2dab4de,0x3bd33ba7,0x3aaf3b47,0xbbdfbbf7,0xa967b012,0x3bfe3bf0,0x399c3a21,0xbb86bbba,0x30122967,0x3bf03bfe,
0x38a9391f,0xbaf5bb44,0x34de32da,0x3ba73bd3,0x3b123ba5,0xbbf0bbfe,0xb257b47e,0x3bd93bb4,0x3a063a88,0xbbb0bbd6,0xa902af8c,0x3bfe3bf2,
0x3919398c,0xbb40bb7e,0x2f8c2902,0x3bf23bfe,0x384238ab,0xbaa2baf7,0x347e3257,0x3bb43bd9,0x3a4c3ac7,0xbbc7bbe4,0xb1d5b420,0x3bdf3bbf,
0x396a39d8,0xbb6dbb9f,0xa89eaef3,0x3bff3bf4,0x389c3900,0xbaecbb31,0x2ef3289e,0x3bf43bff,0x37be383c,0xba46ba9d,0x342031d5,0x3bbf3bdf,
0x399839ff,0xbb83bbae,0xb153b386,0x3be43bca,0x38d73935,0xbb16bb51,0xa839ae5a,0x3bff3bf6,0x3826387d,0xba8abad4,0x2e5a2839,0x3bf63bff,
0x36ff37a3,0xb9e0ba38,0x33863153,0x3bca3be4,0x38f13947,0xbb27bb5b,0xb0d2b2cd,0x3be93bd3,0x384e389e,0xbaadbaed,0xa7a9adc2,0x3bff3bf8,
0x37693800,0xba1aba66,0x2dc227a9,0x3bf83bff,0x364736d6,0xb971b9c8,0x32cd30d2,0x3bd33be9,0x3856389e,0xbab4baed,0xb052b216,0x3bee3bdc,
0x37973810,0xba32ba75,0xa6e0ad2a,0x3bff3bf9,0x36903712,0xb99eb9ea,0x2d2a26e0,0x3bf93bff,0x35943611,0xb8fab94e,0x32163052,0x3bdc3bee,
0x37883800,0xba2aba66,0xafa5b160,0x3bf23be4,0x369f3712,0xb9a7b9ea,0xa617ac93,0x3bff3bfb,0x35bf362e,0xb917b961,0x2c932617,0x3bfb3bff,
0x34e73552,0xb87bb8ca,0x31602fa5,0x3be43bf2,0x367336d6,0xb98cb9c8,0xaea7b0ac,0x3bf53beb,0x35b13611,0xb90db94e,0xa54dabf6,0x3c003bfc,
0x34f43552,0xb885b8ca,0x2bf6254d,0x3bfc3c00,0x343d3498,0xb7ebb83e,0x30ac2ea7,0x3beb3bf5,0x356a35bb,0xb8dcb914,0xada9aff2,0x3bf83bf0,
0x34cb351a,0xb866b8a2,0xa484aac8,0x3c003bfd,0x342f347d,0xb7d5b829,0x2ac82484,0x3bfd3c00,0x332c33c5,0xb6d4b756,0x2ff22da9,0x3bf03bf8,
0x346c34ac,0xb81cb84e,0xacacae8d,0x3bfb3bf5,0x33d9342c,0xb767b7d0,0xa376a999,0x3c003bfe,0x32dd335b,0xb690b6fc,0x29992376,0x3bfe3c00,
0x31e53261,0xb5b3b622,0x2e8d2cac,0x3bf53bfb,0x32ea334d,0xb69bb6f1,0xab5fad2a,0x3bfd3bf9,0x32263288,0xb5eeb645,0xa1e4a86b,0x3c003bff,
0x316331c5,0xb53db596,0x286b21e4,0x3bff3c00,0x30a23103,0xb48ab4e4,0x2d2a2b5f,0x3bf93bfd,0x31093150,0xb4eab52c,0xa967ab91,0x3bfe3bfc,
0x307c30c2,0xb466b4a8,0xa052a67b,0x3c003bff,0x2fde3035,0xb3c0b423,0x267b2052,0x3bff3c00,0x2ec62f52,0xb2b3b33a,0x2b912967,0x3bfc3bfe,
0x2e612eba,0xb251b2a7,0xa6e0a8d0,0x3bff3bff,0x2daf2e08,0xb1a4b1fa,0x9d7fa420,0x3c003c00,0x2cfe2d57,0xb0f6b14d,0x24201d7f,0x3c003c00,
0x2c4d2ca6,0xb048b09f,0x28d026e0,0x3bff3bff,0x297429bf,0xad71adbc,0xa1e4a420,0x3c003c00,0x28dd2928,0xacdbad26,0x98b69f12,0x3c003c00,
0x28462891,0xac44ac90,0x1f1218b6,0x3c003c00,0x275d27f4,0xab5cabf2,0x242021e4,0x3c003c00,0xa344a3a9,0x274427a8,0x1bdb1d7f,0x3c003c00,
0xa27ba2df,0x267b26df,0x124818b6,0x3c003c00,0xa1b2a216,0x25b22616,0x98b69248,0x3c003c00,0xa0e9a14d,0x24e9254d,0x9d7f9bdb,0x3c003c00,
0xac8caccc,0x308630c5,0x24e926e0,0x3c003bff,0xac0eac4d,0x300a3048,0x1bdb21e4,0x3c003c00,0xab20ab9e,0x2f1a2f97,0xa1e49bdb,0x3c003c00,
0xaa24aaa2,0x2e202e9d,0xa6e0a4e9,0x3bff3c00,0xb01cb055,0x340b3441,0x286b2a31,0x3bff3bfe,0xaf52afc5,0x333a33a8,0x1f12254d,0x3c003c00,
0xae6daee0,0x325d32cc,0xa54d9f12,0x3c003c00,0xad89adfb,0x317f31ee,0xaa31a86b,0x3bfe3bff,0xb1f8b24d,0x35c53611,0x2a632c79,0x3bfd3bfb,
0xb150b1a4,0x352c3579,0x211b27a9,0x3c003bff,0xb0a9b0fc,0x349034de,0xa7a9a11b,0x3bff3c00,0xb002b055,0x33e53441,0xac79aa63,0x3bfb3bfd,
0xb3dfb428,0x376c37ca,0x2c2e2ddc,0x3bfc3bf7,0xb2feb36e,0x36ad370d,0x22ad2902,0x3c003bfe,0xb220b28f,0x35e8364b,0xa902a2ad,0x3bfe3c00,
0xb143b1b1,0x35203584,0xaddcac2e,0x3bf73bfc,0xb4eab533,0x387e38b4,0x2d2a2f3f,0x3bf93bf3,0xb45bb4a2,0x380e3846,0x24202a31,0x3c003bfe,
0xb39db414,0x373437a9,0xaa31a420,0x3bfe3c00,0xb288b312,0x364536be,0xaf3fad2a,0x3bf33bf9,0xb5edb647,0x39363971,0x2e283052,0x3bf73bee,
0xb53db594,0x38bb38fa,0x24e92b5f,0x3c003bfd,0xb491b4e7,0x3839387b,0xab5fa4e9,0x3bfd3c00,0xb3d2b43d,0x376137eb,0xb052ae28,0x3bee3bf7,
0xb6fcb769,0x39de3a1a,0x2f263106,0x3bf33be7,0xb627b690,0x395c399e,0x25b22c47,0x3bff3bfb,0xb559b5bf,0x38cf3917,0xac47a5b2,0x3bfb3bff,
0xb491b4f4,0x38393885,0xb106af26,0x3be73bf3,0xb80cb84e,0x3a723aad,0x301231bb,0x3bf03be0,0xb71ab797,0x39ef3a32,0x267b2cde,0x3bff3bfa,
0xb627b69f,0x395c39a7,0xacdea67b,0x3bfa3bff,0xb53db5b1,0x38bb390d,0xb1bbb012,0x3be03bf0,0xb8a2b8f1,0x3af03b27,0x30923271,0x3beb3bd8,
0xb80cb856,0x3a723ab4,0x27442d76,0x3bff3bf9,0xb6fcb788,0x39de3a2a,0xad76a744,0x3bf93bff,0xb5edb673,0x3936398c,0xb271b092,0x3bd83beb,
0xb943b9a1,0x3b583b88,0x31133329,0x3be73bcf,0xb892b8e9,0x3ae43b22,0x28072e0e,0x3bff3bf7,0xb7d9b83e,0x3a533a9f,0xae0ea807,0x3bf73bff,
0xb6a2b73b,0x39a93a01,0xb329b113,0x3bcf3be7,0xb9f0ba61,0x3ba83bcd,0x319433e3,0x3be23bc5,0xb91fb985,0x3b443b7b,0x286b2ea7,0x3bff3bf5,
0xb860b8be,0x3abc3b04,0xaea7a86b,0x3bf53bff,0xb75eb806,0x3a143a6c,0xb3e3b194,0x3bc53be2,0xbaadbb33,0x3bdf3bf5,0x3216344f,0x3bdc3bba,
0xb9b6ba2e,0x3b913bbe,0x28d02f3f,0x3bff3bf3,0xb8d9b945,0x3b183b5a,0xaf3fa8d0,0x3bf33bff,0xb810b872,0x3a753acb,0xb44fb216,0x3bba3bdc,
0xbb7cbc0f,0x3bfb3c00,0x329834ae,0x3bd63bae,0xba59bae5,0x3bca3bea,0x29352fd8,0x3bfe3bf1,0xb95ab9d5,0x3b653b9e,0xafd8a935,0x3bf13bfe,
0xb875b8e4,0x3acd3b1f,0xb4aeb298,0x3bae3bd6,0xbc31bc94,0x3bfe3bee,0x331c350e,0x3bcf3ba1,0xbb09bbae,0x3bef3bfe,0x29993039,0x3bfe3bee,
0xb9e2ba70,0x3ba33bd1,0xb039a999,0x3bee3bfe,0xb8deb95c,0x3b1b3b66,0xb50eb31c,0x3ba13bcf,0xbcb3bd2c,0x3be63bbe,0x33a03570,0x3bc83b93,
0xbbcabc47,0x3bff3bfb,0x29fe3085,0x3bfe3bec,0xba73bb17,0x3bd13bf1,0xb085a9fe,0x3bec3bfe,0xb94cb9da,0x3b5d3ba0,0xb570b3a0,0x3b933bc8,
0x387238f8,0xbacbbb2c,0x38b4376f,0x3ae53b41,0x36f837e8,0xb9dbba5b,0x3b1639cf,0x39fd3a79,0x35333611,0xb8b4b94e,0x3d3b3c4d,0x38dc3973,
0x3312345b,0xb6beb80e,0x400b3e70,0x37183839,0x381e3896,0xba82bae7,0x385936e7,0x3b073b58,0x367a3756,0xb991ba10,0x3a743956,0x3a3a3aa8,
0x34d935a6,0xb871b906,0x3ca53bbf,0x393939bf,0x329c3411,0xb656b7a4,0x3ed43d99,0x380b38a7,0x37973838,0xba32ba9a,0x38013662,0x3b273b6e,
0x35ff36c7,0xb942b9bf,0x39de38e3,0x3a733ad4,0x3480353d,0xb82cb8bb,0x3c223afa,0x39913a08,0x32263390,0xb5eeb729,0x3dd73ce6,0x38853910,
0x36f837ba,0xb9dbba44,0x375835e1,0x3b453b82,0x3586363c,0xb8f0b96a,0x39523876,0x3aa93afd,0x342834d5,0xb7cab86e,0x3b5a3a46,0x39e43a4c,
0x31b132fe,0xb584b6ad,0x3d0a3c4d,0x38fa3973,0x365d370a,0xb97eb9e6,0x36b33562,0x3b613b95,0x351035b4,0xb89ab910,0x38ce380d,0x3adc3b23,
0x33a3346f,0xb73ab81e,0x3a8939a0,0x3a323a8b,0x313d326e,0xb51ab62e,0x3c5e3b8f,0x396739d1,0x35c63661,0xb91cb981,0x361334e5,0x3b7b3ba6,
0x349b352f,0xb841b8b1,0x38513750,0x3b0a3b47,0x32f8340a,0xb6a7b799,0x39cb3906,0x3a7b3ac6,0x30c931de,0xb4aeb5ae,0x3b953aa3,0x39cf3a28,
0x353335bb,0xb8b4b914,0x3577346a,0x3b923bb6,0x342834ac,0xb7cab84e,0x37b4368e,0x3b353b67,0x324d334d,0xb611b6f1,0x391c3876,0x3abe3afd,
0x30553150,0xb441b52c,0x3a9339cf,0x3a2e3a79,0x34a2351a,0xb846b8a2,0x34de33e3,0x3ba73bc5,0x336e342c,0xb70db7d0,0x36d135d2,0x3b5c3b85,
0x31a43288,0xb579b645,0x387a37db,0x3afb3b2e,0x2fc530c2,0xb3a8b4a8,0x39ae390f,0x3a863ac3,0x3414347d,0xb7a9b829,0x344832f4,0x3bba3bd1,
0x328f335b,0xb64bb6fc,0x35f6351c,0x3b7f3b9f,0x30fc31c5,0xb4deb596,0x37c336d8,0x3b333b5b,0x2ee03035,0xb2ccb423,0x38df385d,0x3ad53b06,
0x331233c5,0xb6beb756,0x336b3209,0x3bcb3bdd,0x31b13261,0xb584b622,0x3523346a,0x3b9e3bb6,0x30553103,0xb441b4e4,0x36a435e1,0x3b643b82,
0x2dfb2f52,0xb1eeb33a,0x3821376f,0x3b1c3b41,0x31ff3295,0xb5cbb651,0x324a3120,0x3bda3be6,0x30d6316a,0xb4bab543,0x34563378,0x3bb93bca,
0x2f5f3042,0xb346b42f,0x359334f3,0x3b8e3ba5,0x2d172e3b,0xb10fb22c,0x36e03637,0x3b5a3b75,0x30ef316a,0xb4d2b543,0x312d3039,0x3be63bee,
0x2ff83075,0xb3d9b460,0x331c3223,0x3bcf3bdb,0x2e152f06,0xb207b2f0,0x348c340c,0x3bb23bc1,0x2c342d24,0xb02fb11c,0x3593350e,0x3b8e3ba1,
0x2fc53042,0xb3a8b42f,0x30122ea7,0x3bf03bf5,0x2e472f06,0xb238b2f0,0x319430d2,0x3be23be9,0x2ccc2d89,0xb0c5b17f,0x331c3257,0x3bcf3bd9,
0x2aa22c0e,0xae9db00a,0x345633e3,0x3bb93bc5,0x2daf2e3b,0xb1a4b22c,0x2df52cde,0x3bf73bfa,0x2c992d24,0xb093b11c,0x30122f0c,0x3bf03bf4,
0x2b072c0e,0xaf01b00a,0x312d309f,0x3be63beb,0x28dd29f2,0xacdbadee,0x324a31bb,0x3bda3be0,0x2b392bea,0xaf33afe2,0x2b912a31,0x3bfc3bfe,
0x29d82a89,0xadd5ae84,0x2d2a2c79,0x3bf93bfb,0x28782928,0xac77ad26,0x2e8d2ddc,0x3bf53bf7,0x26302790,0xaa2fab8e,0x2ff22f3f,0x3bf03bf3,
0x263026c7,0xaa2faac5,0x267b254d,0x3bff3c00,0x25022599,0xa901a998,0x286b27a9,0x3bff3bff,0x23a9246b,0xa7a8a86b,0x29992902,0x3bfe3bfe,
0x214d227b,0xa54da67b,0x2ac82a31,0x3bfd3bfe,0xa020a084,0x24202484,0xa0529f12,0x3c003c00,0x9ead9f76,0x22ad2376,0xa1e4a11b,0x3c003c00,
0x9d1b9de4,0x211b21e4,0xa376a2ad,0x3c003c00,0x9b129c52,0x1f122052,0xa484a420,0x3c003c00,0xa928a9a6,0x2d262da3,0xa967a86b,0x3bfe3bff,
0xa82da8aa,0x2c2b2ca9,0xab5faa63,0x3bfd3bfd,0xa662a75d,0x2a612b5c,0xacacac2e,0x3bfb3bfc,0xa46ba567,0x286b2966,0xada9ad2a,0x3bf83bf9,
0xaca6ad17,0x309f310f,0xacdeabf6,0x3bfa3bfc,0xab85ac34,0x2f7e302f,0xaea7adc2,0x3bf53bf8,0xa9bfaaa2,0x2dbc2e9d,0xb039af8c,0x3bee3bf2,
0xa7f4a8dd,0x2bf22cdb,0xb120b0ac,0x3be63beb,0xaebaaf5f,0x32a73346,0xaf0cadc2,0x3bf43bf8,0xad70ae15,0x31663207,0xb0d2b02c,0x3be93bef,
0xac27accc,0x302330c5,0xb223b17a,0x3bdb3be3,0xa9bfab07,0x2dbc2f01,0xb378b2cd,0x3bca3bd3,0xb069b0d6,0x345434ba,0xb09faf8c,0x3beb3bf2,
0xaf1faff8,0x330933d9,0xb257b17a,0x3bd93be3,0xad70ae47,0x31663238,0xb40cb336,0x3bc13bce,0xab85ac99,0x2f7e3093,0xb4f3b47e,0x3ba53bb4,
0xb177b1ff,0x354f35cb,0xb1bbb0ac,0x3be03beb,0xb069b0ef,0x345434d2,0xb3e3b2cd,0x3bc53bd3,0xaebaafc5,0x32a733a8,0xb50eb47e,0x3ba13bb4,
0xaca6adaf,0x309f31a4,0xb637b5a1,0x3b753b8c,0xb288b32c,0x364536d4,0xb2dab194,0x3bd33be2,0xb143b1e5,0x352035b3,0xb4bcb413,0x3bac3bc1,
0xb002b0a2,0x33e5348a,0xb61ab569,0x3b7a3b94,0xad89aec6,0x317f32b3,0xb78db6d1,0x3b3c3b5c,0xb39db42f,0x373437d5,0xb3fdb27e,0x3bc33bd7,
0xb220b2dd,0x35e83690,0xb58cb4c3,0x3b8f3bab,0xb0a9b163,0x3490353d,0xb732b65b,0x3b4c3b6f,0xae6dafde,0x325d33c0,0xb87eb809,0x3afa3b25,
0xb45bb4cb,0x380e3866,0xb493b36b,0x3bb13bcb,0xb2feb3d9,0x36ad3767,0xb662b577,0x3b6e3b92,0xb150b226,0x352c35ee,0xb82db758,0x3b183b45,
0xaf52b07c,0x333a3466,0xb944b8b4,0x3aaf3ae5,0xb4eab56a,0x387e38dc,0xb52ab42e,0x3b9d3bbe,0xb3dfb46c,0x376c381c,0xb741b630,0x3b493b76,
0xb1f8b2ea,0x35c5369b,0xb8c9b831,0x3add3b16,0xb01cb109,0x340b34ea,0xba1eb96d,0x3a5b3a9f,0xb57cb60d,0x38e8394b,0xb5c4b4a7,0x3b873baf,
0xb462b4ed,0x38133880,0xb815b6ee,0x3b203b57,0xb2a2b3b1,0x365c3745,0xb972b8bd,0x3a9d3ae2,0xb08fb197,0x3478356d,0xbb10ba37,0x39ff3a51,
0xb611b6b5,0x394e39b4,0xb662b523,0x3b6e3b9e,0xb4d5b571,0x386e38e1,0xb88eb7b4,0x3af43b35,0xb34db43d,0x36f137eb,0xba28b952,0x3a573aa9,
0xb103b226,0x34e435ee,0xbc11bb16,0x399c39fd,0xb6aab761,0x39ae3a16,0xb705b5a1,0x3b533b8c,0xb54bb5f8,0x38c5393d,0xb90fb841,0x3ac33b10,
0xb3fab4a2,0x37833846,0xbaefb9f1,0x3a0c3a6c,0xb177b2b6,0x354f366d,0xbcb0bc08,0x393139a3,0xb747b80a,0x3a083a70,0xb7acb621,0x3b373b78,
0xb5c2b681,0x39193995,0xb997b8ac,0x3a8f3ae9,0xb454b509,0x38093895,0xbbcbba9e,0x39bb3a2a,0xb1ebb347,0x35b936eb,0xbd6bbc96,0x38c03942,
0xb7e8b866,0x3a5b3ac1,0xb82db6a4,0x3b183b64,0xb63cb70e,0x396a39e8,0xba28b91c,0x3a573abe,0xb4acb571,0x384e38e1,0xbc61bb5a,0x396539e4,
0xb261b3d9,0x36223767,0xbe4ebd3b,0x384938dc,0xb848b8c6,0x3aa83b0a,0xb886b72a,0x3af73b4d,0xb6b9b79f,0x39b73a36,0xbac3b992,0x3a1c3a91,
0xb506b5db,0x3892392a,0xbcedbc15,0x390b399a,0xb2d7b436,0x368a37e0,0xbf6abdff,0x37993871,0xb533b611,0x38b4394e,0x2ca62630,0xb09faa2f,
0xb312b45b,0x36be380e,0x31772fc5,0xb54fb3a8,0xafc5b177,0x33a8354f,0x345b3312,0xb80eb6be,0xa630aca6,0x2a2f309f,0x36113533,0xb94eb8b4,
0xb4d9b5a6,0x38713906,0x2c5a25cb,0xb055a9ca,0xb29cb411,0x365637a4,0x311c2f45,0xb4fcb32e,0xaf45b11c,0x332e34fc,0x3411329c,0xb7a4b656,
0xa5cbac5a,0x29ca3055,0x35a634d9,0xb906b871,0xb480b53d,0x382c38bb,0x2c0e2567,0xb00aa966,0xb226b390,0x35ee3729,0x30c22ec6,0xb4a8b2b3,
0xaec6b0c2,0x32b334a8,0x33903226,0xb729b5ee,0xa567ac0e,0x2966300a,0x353d3480,0xb8bbb82c,0xb428b4d5,0x37ca386e,0x2b852502,0xaf7ea901,
0xb1b1b2fe,0x358436ad,0x30692e47,0xb454b238,0xae47b069,0x32383454,0x32fe31b1,0xb6adb584,0xa502ab85,0x29012f7e,0x34d53428,0xb86eb7ca,
0xb3a3b46f,0x373a381e,0x2aee249d,0xaee8a89d,0xb13db26e,0x351a362e,0x300f2dc9,0xb3fdb1bd,0xadc9b00f,0x31bd33fd,0x326e313d,0xb62eb51a,
0xa49daaee,0x289d2ee8,0x346f33a3,0xb81eb73a,0xb2f8b40a,0x36a73799,0x2a562439,0xae52a839,0xb0c9b1de,0x34ae35ae,0x2f6c2d4a,0xb352b141,
0xad4aaf6c,0x31413352,0x31de30c9,0xb5aeb4ae,0xa439aa56,0x28392e52,0x340a32f8,0xb799b6a7,0xb24db34d,0x361136f1,0x29bf23a9,0xadbca7a8,
0xb055b150,0x3441352c,0x2eba2ccc,0xb2a7b0c5,0xacccaeba,0x30c532a7,0x31503055,0xb52cb441,0xa3a9a9bf,0x27a82dbc,0x334d324d,0xb6f1b611,
0xb1a4b288,0x35793645,0x292822df,0xad26a6df,0xafc5b0c2,0x33a834a8,0x2e082c4d,0xb1fab048,0xac4dae08,0x304831fa,0x30c22fc5,0xb4a8b3a8,
0xa2dfa928,0x26df2d26,0x328831a4,0xb645b579,0xb0fcb1c5,0x34de3596,0x28912216,0xac90a616,0xaee0b035,0x32cc3423,0x2d572b9e,0xb14daf97,
0xab9ead57,0x2f97314d,0x30352ee0,0xb423b2cc,0xa216a891,0x26162c90,0x31c530fc,0xb596b4de,0xb055b103,0x344134e4,0x27f4214d,0xabf2a54d,
0xadfbaf52,0x31ee333a,0x2ca62aa2,0xb09fae9d,0xaaa2aca6,0x2e9d309f,0x2f522dfb,0xb33ab1ee,0xa14da7f4,0x254d2bf2,0x31033055,0xb4e4b441,
0xaf5fb042,0x3346342f,0x26c72084,0xaac5a484,0xad17ae3b,0x310f322c,0x2bea29a6,0xafe2ada3,0xa9a6abea,0x2da32fe2,0x2e3b2d17,0xb22cb10f,
0xa084a6c7,0x24842ac5,0x30422f5f,0xb42fb346,0xae15af06,0x320732f0,0x25991f76,0xa998a376,0xac34ad24,0x302f311c,0x2a8928aa,0xae84aca9,
0xa8aaaa89,0x2ca92e84,0x2d242c34,0xb11cb02f,0x9f76a599,0x23762998,0x2f062e15,0xb2f0b207,0xacccad89,0x30c5317f,0x246b1de4,0xa86ba1e4,
0xaaa2ac0e,0x2e9d300a,0x2928275d,0xad26ab5c,0xa75da928,0x2b5c2d26,0x2c0e2aa2,0xb00aae9d,0x9de4a46b,0x21e4286b,0x2d892ccc,0xb17fb0c5,
0xab07ac0e,0x2f01300a,0x227b1c52,0xa67ba052,0xa8dda9f2,0x2cdb2dee,0x27902567,0xab8ea966,0xa567a790,0x29662b8e,0x29f228dd,0xadeeacdb,
0x9c52a27b,0x2052267b,0x2c0e2b07,0xb00aaf01,0xa878a928,0x2c772d26,0x2020197f,0xa4209d7f,0xa630a790,0x2a2f2b8e,0x24d022df,0xa8cfa6df,
0xa2dfa4d0,0x26df28cf,0x27902630,0xab8eaa2f,0x997fa020,0x1d7f2420,0x29282878,0xad26ac77,0xa3a9a46b,0x27a8286b,0x1b1214b6,0x9f1298b6,
0xa14da27b,0x254d267b,0x20201de4,0xa420a1e4,0x9de4a020,0x21e42420,0x227b214d,0xa67ba54d,0x94b69b12,0x18b61f12,0x246b23a9,0xa86ba7a8,
0x1d1b1de4,0xa11ba1e4,0x94b68e48,0x18b61248,0x1b121c52,0x9f12a052,0x997f97db,0x1d7f1bdb,0x17db197f,0x9bdb9d7f,0x9c529b12,0x20521f12,
0xe4814b6,0x924898b6,0x9de49d1b,0x21e4211b,0x2662275d,0xaa61ab5c,0x9de497db,0x21e41bdb,0x246b2567,0xa86ba966,0xa2dfa0e9,0x26df24e9,
0x20e922df,0xa4e9a6df,0xa567a46b,0x2966286b,0x17db1de4,0x9bdba1e4,0xa75da662,0x2b5c2a61,0x29bf2aa2,0xadbcae9d,0xa14d9b12,0x254d1f12,
0x27f428dd,0xabf2acdb,0xa630a46b,0x2a2f286b,0x246b2630,0xa86baa2f,0xa8dda7f4,0x2cdb2bf2,0x1b12214d,0x9f12a54d,0xaaa2a9bf,0x2e9d2dbc,
0x2c272ccc,0xb023b0c5,0xa3a99d1b,0x27a8211b,0x29bf2b07,0xadbcaf01,0xa878a662,0x2c772a61,0x26622878,0xaa61ac77,0xab07a9bf,0x2f012dbc,
0x1d1b23a9,0xa11ba7a8,0xacccac27,0x30c53023,0x2d702e47,0xb166b238,0xa5029ead,0x290122ad,0x2b852c99,0xaf7eb093,0xa9d8a82d,0x2dd52c2b,
0x282d29d8,0xac2badd5,0xac99ab85,0x30932f7e,0x1ead2502,0xa2ada901,0xae47ad70,0x32383166,0x2eba2fc5,0xb2a7b3a8,0xa630a020,0x2a2f2420,
0x2ca62daf,0xb09fb1a4,0xab39a928,0x2f332d26,0x29282b39,0xad26af33,0xadafaca6,0x31a4309f,0x20202630,0xa420aa2f,0xafc5aeba,0x33a832a7,
0x300230a2,0xb3e5b48a,0xa75da0e9,0x2b5c24e9,0x2d892ec6,0xb17fb2b3,0xac4daa24,0x30482e20,0x2a242c4d,0xae20b048,0xaec6ad89,0x32b3317f,
0x20e9275d,0xa4e9ab5c,0xb0a2b002,0x348a33e5,0x30a93163,0xb490b53d,0xa846a1b2,0x2c4425b2,0x2e6d2fde,0xb25db3c0,0xacfeab20,0x30f62f1a,
0x2b202cfe,0xaf1ab0f6,0xafdeae6d,0x33c0325d,0x21b22846,0xa5b2ac44,0xb163b0a9,0x353d3490,0x31503226,0xb52cb5ee,0xa8dda27b,0x2cdb267b,
0x2f52307c,0xb33ab466,0xadafac0e,0x31a4300a,0x2c0e2daf,0xb00ab1a4,0xb07caf52,0x3466333a,0x227b28dd,0xa67bacdb,0xb226b150,0x35ee352c,
0x31f832ea,0xb5c5b69b,0xa974a344,0x2d712744,0x301c3109,0xb40bb4ea,0xae61ac8c,0x32513086,0x2c8c2e61,0xb086b251,0xb109b01c,0x34ea340b,
0x23442974,0xa744ad71,0xb2eab1f8,0x369b35c5,0x32a233b1,0xb65cb745,0xaa0ba407,0x2e072806,0x308f3197,0xb478b56d,0xaf13ad0b,0x32fd3103,
0x2d0b2f13,0xb103b2fd,0xb197b08f,0x356d3478,0x24072a0b,0xa806ae07,0xb3b1b2a2,0x3745365c,0x334d343d,0xb6f1b7eb,0xaaa2a46b,0x2e9d286b,
0x31033226,0xb4e4b5ee,0xafc5ad89,0x33a8317f,0x2d892fc5,0xb17fb3a8,0xb226b103,0x35ee34e4,0x246b2aa2,0xa86bae9d,0xb43db34d,0x37eb36f1,
0x33fa34a2,0xb783b846,0xab39a4d0,0x2f3328cf,0x317732b6,0xb54fb66d,0xb03cae08,0x342931fa,0x2e08303c,0xb1fab429,0xb2b6b177,0x366d354f,
0x24d02b39,0xa8cfaf33,0xb4a2b3fa,0x38463783,0x34543509,0xb809b895,0xabd1a534,0x2fc92934,0x31eb3347,0xb5b9b6eb,0xb095ae87,0x347e3276,
0x2e873095,0xb276b47e,0xb347b1eb,0x36eb35b9,0x25342bd1,0xa934afc9,0xb509b454,0x38953809,0x34ac3571,0xb84eb8e1,0xac34a599,0x302f2998,
0x326133d9,0xb622b767,0xb0efaf06,0x34d232f0,0x2f0630ef,0xb2f0b4d2,0xb3d9b261,0x37673622,0x25992c34,0xa998b02f,0xb571b4ac,0x38e1384e,
0x350635db,0xb892b92a,0xac80a5fd,0x307a29fd,0x32d73436,0xb68ab7e0,0xb14aaf85,0x3526336b,0x2f85314a,0xb36bb526,0xb436b2d7,0x37e0368a,
0x25fd2c80,0xa9fdb07a,0xb5dbb506,0x392a3892,0,0,0,0,0,0,0,0,
0,0,0,0,0,0,0,0,0,0,0,0,
0,0,0,0,0,0,0,0,0,0,0,0,
0,0,0,0,0,0,0,0,0,0,0,0,
0,0,0,0,0,0,0,0,0,0,0,0,
0,0,0,0,0,0,0,0,0,0,0,0,
0,0,0,0,0,0,0,0,0,0,0,0,
0,0,0,0,0,0,0,0,0,0,0,0,
0,0,0,0,0,0,0,0,0,0,0,0,
0,0,0,0,0,0,0,0,0,0,0,0,
0,0,0,0,0,0,0,0,0,0,0,0,
0,0,0,0,0,0,0,0,0,0,0,0,
0,0,0,0,0,0,0,0,0,0,0,0,
0,0,0,0,0,0,0,0,0,0,0,0,
0,0,0,0,0,0,0,0,0,0,0,0,
0,0,0,0,0,0,0,0,0,0,0,0,
0,0,0,0,0,0,0,0,0,0,0,0,
0,0,0,0,0,0,0,0,0,0,0,0,
0,0,0,0,0,0,0,0,0,0,0,0,
0,0,0,0,0,0,0,0,0,0,0,0,
0,0,0,0,0,0,0,0,0,0,0,0,
0,0,0,0,0,0,0,0,0,0,0,0,
0,0,0,0,0,0,0,0,0,0,0,0,
0,0,0,0,0,0,0,0,0,0,0,0,
0,0,0,0,0,0,0,0,0,0,0,0,
0,0,0,0,0,0,0,0,0,0,0,0,
0,0,0,0,0,0,0,0,0,0,0,0,
0,0,0,0,0,0,0,0,0,0,0,0,
0,0,0,0,0,0,0,0,0,0,0,0,
0,0,0,0,0,0,0,0,0,0,0,0,
0,0,0,0,0,0,0,0,0,0,0,0,
0,0,0,0,0,0,0,0,0,0,0,0,
0,0,0,0,0,0,0,0,0,0,0,0,
0,0,0,0,0,0,0,0,0,0,0,0,
0,0,0,0,0,0,0,0,0,0,0,0,
0,0,0,0,0,0,0,0,0,0,0,0,
0,0,0,0,0,0,0,0,0,0,0,0,
0,0,0,0,0,0,0,0,0,0,0,0,
0,0,0,0,0,0,0,0,0,0,0,0,
0,0,0,0,0,0,0,0,0,0,0,0,
0,0,0,0,0,0,0,0,0,0,0,0,
0,0,0,0,0,0,0,0,0,0,0,0,
0,0,0,0,0,0,0,0,0,0,0,0,
0x2bf62c00,0x2ba82bd9,0x2b0e2b64,0x2a2f2aa7,0x2b0e2c00,0x1e462872,0xaa2fa61f,0xaba8abd9,0x29132c00,0xab0ea23e,0xa4a5ab64,0x2bf62872,
0x24a52c00,0xaa2faaa7,0x2bf6261f,0xab0e223e,0x9e462c00,0x24a5abd9,0xa78b2b64,0x2913aaa7,0xa78b2c00,0x2bf6a872,0xa913a61f,0xa4a52bd9,
0xaa2f2c00,0x278b223e,0x2ba8ab64,0x9e46a872,0xaba82c00,0xa9132aa7,0x9e46261f,0x278ba23e,0x1e460000,0x24a5223e,0x278b261f,0x29132872,
0x278b0000,0x2bf62aa7,0x29132b64,0xa4a5223e,0x2a2f0000,0x278b2bd9,0xaba8a61f,0x9e46aaa7,0x2ba80000,0xa9132872,0x1e46ab64,0x278b2bd9,
0x2bf60000,0xaba8a23e,0x2b0e261f,0xaa2fa872,0x2b0e0000,0x9e46aaa7,0xaa2f2b64,0x2ba8a23e,0x29130000,0x2b0eabd9,0xa4a5a61f,0xabf62aa7,
0x24a50000,0x2a2fa872,0x2bf6ab64,0x2b0eabd9,0x291329a8,0x278b2872,0x24a5261f,0x1e46223e,0xa4a5a9a8,0x2913223e,0x2bf62b64,0x278b2aa7,
0x9e4629a8,0xaba8aaa7,0x278ba61f,0x2a2f2bd9,0x278ba9a8,0x1e462bd9,0xa913ab64,0x2ba82872,0xaa2f29a8,0x2b0ea872,0xaba8261f,0x2bf6a23e,
0x2ba8a9a8,0xaa2fa23e,0x9e462b64,0x2b0eaaa7,0xabf629a8,0xa4a52aa7,0x2b0ea61f,0x2913abd9,0x2b0ea9a8,0x2bf6abd9,0x2a2fab64,0x24a5a872,
0x2a2f29a8,0x2b0e2aa7,0x2ba82b64,0x2bf62bd9,0xaba8a9a8,0xaa2fabd9,0x1e46a61f,0x2b0e2872,0x2bf629a8,0xa4a52872,0xab0eab64,0x2913a23e,
0xab0ea9a8,0x2bf6223e,0xaa2f261f,0x24a5aaa7,0x291329a8,0xa78baaa7,0x24a52b64,0x9e46abd9,0xa4a5a9a8,0xa9132bd9,0x2bf6a61f,0xa78ba872,
0x9e4629a8,0x2ba8a872,0x278bab64,0xaa2f223e,0x278ba9a8,0x9e46a23e,0xa913261f,0xaba82aa7,0xabf62c00,0xaba82bd9,0xab0e2b64,0xaa2f2aa7,
0xab0e2c00,0x9e462872,0x2a2fa61f,0x2ba8abd9,0xa9132c00,0x2b0ea23e,0x24a5ab64,0xabf62872,0xa4a52c00,0x2a2faaa7,0xabf6261f,0x2b0e223e,
0x1e462c00,0xa4a5abd9,0x278b2b64,0xa913aaa7,0x278b2c00,0xabf6a872,0x2913a61f,0x24a52bd9,0x2a2f2c00,0xa78b223e,0xaba8ab64,0x1e46a872,
0x2ba82c00,0x29132aa7,0x1e46261f,0xa78ba23e,0x9e460000,0xa4a5223e,0xa78b261f,0xa9132872,0xa78b0000,0xabf62aa7,0xa9132b64,0x24a5223e,
0xaa2f0000,0xa78b2bd9,0x2ba8a61f,0x1e46aaa7,0xaba80000,0x29132872,0x9e46ab64,0xa78b2bd9,0xabf60000,0x2ba8a23e,0xab0e261f,0x2a2fa872,
0xab0e0000,0x1e46aaa7,0x2a2f2b64,0xaba8a23e,0xa9130000,0xab0eabd9,0x24a5a61f,0x2bf62aa7,0xa4a50000,0xaa2fa872,0xabf6ab64,0xab0eabd9,
0xa91329a8,0xa78b2872,0xa4a5261f,0x9e46223e,0x24a5a9a8,0xa913223e,0xabf62b64,0xa78b2aa7,0x1e4629a8,0x2ba8aaa7,0xa78ba61f,0xaa2f2bd9,
0xa78ba9a8,0x9e462bd9,0x2913ab64,0xaba82872,0x2a2f29a8,0xab0ea872,0x2ba8261f,0xabf6a23e,0xaba8a9a8,0x2a2fa23e,0x1e462b64,0xab0eaaa7,
0x2bf629a8,0x24a52aa7,0xab0ea61f,0xa913abd9,0xab0ea9a8,0xabf6abd9,0xaa2fab64,0xa4a5a872,0xaa2f29a8,0xab0e2aa7,0xaba82b64,0xabf62bd9,
0x2ba8a9a8,0x2a2fabd9,0x9e46a61f,0xab0e2872,0xabf629a8,0x24a52872,0x2b0eab64,0xa913a23e,0x2b0ea9a8,0xabf6223e,0x2a2f261f,0xa4a5aaa7,
0xa91329a8,0x278baaa7,0xa4a52b64,0x1e46abd9,0x24a5a9a8,0x29132bd9,0xabf6a61f,0x278ba872,0x1e4629a8,0xaba8a872,0xa78bab64,0x2a2f223e,
0xa78ba9a8,0x1e46a23e,0x2913261f,0x2ba82aa7,0x9e460000,0xa4a5a23e,0xa78ba61f,0xa913a872,0xa78b0000,0xabf6aaa7,0xa913ab64,0x24a5a23e,
0xaa2f0000,0xa78babd9,0x2ba8261f,0x1e462aa7,0xaba80000,0x2913a872,0x9e462b64,0xa78babd9,0xabf60000,0x2ba8223e,0xab0ea61f,0x2a2f2872,
0xab0e0000,0x1e462aa7,0x2a2fab64,0xaba8223e,0xa9130000,0xab0e2bd9,0x24a5261f,0x2bf6aaa7,0xa4a50000,0xaa2f2872,0xabf62b64,0xab0e2bd9,
0x2bf62c00,0x2ba82bd9,0x2b0e2b64,0x2a2f2aa7,0x2b0e2c00,0x1e462872,0xaa2fa61f,0xaba8abd9,0x29132c00,0xab0ea23e,0xa4a5ab64,0x2bf62872,
0x24a52c00,0xaa2faaa7,0x2bf6261f,0xab0e223e,0x9e462c00,0x24a5abd9,0xa78b2b64,0x2913aaa7,0xa78b2c00,0x2bf6a872,0xa913a61f,0xa4a52bd9,
0xaa2f2c00,0x278b223e,0x2ba8ab64,0x9e46a872,0xaba82c00,0xa9132aa7,0x9e46261f,0x278ba23e,0xaa2fa9a8,0xab0eaaa7,0xaba8ab64,0xabf6abd9,
0x2ba829a8,0x2a2f2bd9,0x9e46261f,0xab0ea872,0xabf6a9a8,0x24a5a872,0x2b0e2b64,0xa913223e,0x2b0e29a8,0xabf6a23e,0x2a2fa61f,0xa4a52aa7,
0xa913a9a8,0x278b2aa7,0xa4a5ab64,0x1e462bd9,0x24a529a8,0x2913abd9,0xabf6261f,0x278b2872,0x1e46a9a8,0xaba82872,0xa78b2b64,0x2a2fa23e,
0xa78b29a8,0x1e46223e,0x2913a61f,0x2ba8aaa7,0x291329a8,0x278b2872,0x24a5261f,0x1e46223e,0xa4a5a9a8,0x2913223e,0x2bf62b64,0x278b2aa7,
0x9e4629a8,0xaba8aaa7,0x278ba61f,0x2a2f2bd9,0x278ba9a8,0x1e462bd9,0xa913ab64,0x2ba82872,0xaa2f29a8,0x2b0ea872,0xaba8261f,0x2bf6a23e,
0x2ba8a9a8,0xaa2fa23e,0x9e462b64,0x2b0eaaa7,0xabf629a8,0xa4a52aa7,0x2b0ea61f,0x2913abd9,0x2b0ea9a8,0x2bf6abd9,0x2a2fab64,0x24a5a872,
0x1e460000,0x24a5a23e,0x278ba61f,0x2913a872,0x278b0000,0x2bf6aaa7,0x2913ab64,0xa4a5a23e,0x2a2f0000,0x278babd9,0xaba8261f,0x9e462aa7,
0x2ba80000,0xa913a872,0x1e462b64,0x278babd9,0x2bf60000,0xaba8223e,0x2b0ea61f,0xaa2f2872,0x2b0e0000,0x9e462aa7,0xaa2fab64,0x2ba8223e,
0x29130000,0x2b0e2bd9,0xa4a5261f,0xabf6aaa7,0x24a50000,0x2a2f2872,0x2bf62b64,0x2b0e2bd9,0xabf62c00,0xaba82bd9,0xab0e2b64,0xaa2f2aa7,
0xab0e2c00,0x9e462872,0x2a2fa61f,0x2ba8abd9,0xa9132c00,0x2b0ea23e,0x24a5ab64,0xabf62872,0xa4a52c00,0x2a2faaa7,0xabf6261f,0x2b0e223e,
0x1e462c00,0xa4a5abd9,0x278b2b64,0xa913aaa7,0x278b2c00,0xabf6a872,0x2913a61f,0x24a52bd9,0x2a2f2c00,0xa78b223e,0xaba8ab64,0x1e46a872,
0x2ba82c00,0x29132aa7,0x1e46261f,0xa78ba23e,0x2a2fa9a8,0x2b0eaaa7,0x2ba8ab64,0x2bf6abd9,0xaba829a8,0xaa2f2bd9,0x1e46261f,0x2b0ea872,
0x2bf6a9a8,0xa4a5a872,0xab0e2b64,0x2913223e,0xab0e29a8,0x2bf6a23e,0xaa2fa61f,0x24a52aa7,0x2913a9a8,0xa78b2aa7,0x24a5ab64,0x9e462bd9,
0xa4a529a8,0xa913abd9,0x2bf6261f,0xa78b2872,0x9e46a9a8,0x2ba82872,0x278b2b64,0xaa2fa23e,0x278b29a8,0x9e46223e,0xa913a61f,0xaba8aaa7,
0xa91329a8,0xa78b2872,0xa4a5261f,0x9e46223e,0x24a5a9a8,0xa913223e,0xabf62b64,0xa78b2aa7,0x1e4629a8,0x2ba8aaa7,0xa78ba61f,0xaa2f2bd9,
0xa78ba9a8,0x9e462bd9,0x2913ab64,0xaba82872,0x2a2f29a8,0xab0ea872,0x2ba8261f,0xabf6a23e,0xaba8a9a8,0x2a2fa23e,0x1e462b64,0xab0eaaa7,
0x2bf629a8,0x24a52aa7,0xab0ea61f,0xa913abd9,0xab0ea9a8,0xabf6abd9,0xaa2fab64,0xa4a5a872,0x2ba82c00,0x29132aa7,0x1e46261f,0xa78ba23e,
0x2a2f2c00,0xa78b223e,0xaba8ab64,0x1e46a872,0x278b2c00,0xabf6a872,0x2913a61f,0x24a52bd9,0x1e462c00,0xa4a5abd9,0x278b2b64,0xa913aaa7,
0xa4a52c00,0x2a2faaa7,0xabf6261f,0x2b0e223e,0xa9132c00,0x2b0ea23e,0x24a5ab64,0xabf62872,0xab0e2c00,0x9e462872,0x2a2fa61f,0x2ba8abd9,
0xabf62c00,0xaba82bd9,0xab0e2b64,0xaa2f2aa7,0x24a50000,0x2a2f2872,0x2bf62b64,0x2b0e2bd9,0x29130000,0x2b0e2bd9,0xa4a5261f,0xabf6aaa7,
0x2b0e0000,0x9e462aa7,0xaa2fab64,0x2ba8223e,0x2bf60000,0xaba8223e,0x2b0ea61f,0xaa2f2872,0x2ba80000,0xa913a872,0x1e462b64,0x278babd9,
0x2a2f0000,0x278babd9,0xaba8261f,0x9e462aa7,0x278b0000,0x2bf6aaa7,0x2913ab64,0xa4a5a23e,0x1e460000,0x24a5a23e,0x278ba61f,0x2913a872,
0xab0ea9a8,0xabf6abd9,0xaa2fab64,0xa4a5a872,0x2bf629a8,0x24a52aa7,0xab0ea61f,0xa913abd9,0xaba8a9a8,0x2a2fa23e,0x1e462b64,0xab0eaaa7,
0x2a2f29a8,0xab0ea872,0x2ba8261f,0xabf6a23e,0xa78ba9a8,0x9e462bd9,0x2913ab64,0xaba82872,0x1e4629a8,0x2ba8aaa7,0xa78ba61f,0xaa2f2bd9,
0x24a5a9a8,0xa913223e,0xabf62b64,0xa78b2aa7,0xa91329a8,0xa78b2872,0xa4a5261f,0x9e46223e,0x278b29a8,0x9e46223e,0xa913a61f,0xaba8aaa7,
0x9e46a9a8,0x2ba82872,0x278b2b64,0xaa2fa23e,0xa4a529a8,0xa913abd9,0x2bf6261f,0xa78b2872,0x2913a9a8,0xa78b2aa7,0x24a5ab64,0x9e462bd9,
0xab0e29a8,0x2bf6a23e,0xaa2fa61f,0x24a52aa7,0x2bf6a9a8,0xa4a5a872,0xab0e2b64,0x2913223e,0xaba829a8,0xaa2f2bd9,0x1e46261f,0x2b0ea872,
0x2a2fa9a8,0x2b0eaaa7,0x2ba8ab64,0x2bf6abd9,0xaba82c00,0xa9132aa7,0x9e46261f,0x278ba23e,0xaa2f2c00,0x278b223e,0x2ba8ab64,0x9e46a872,
0xa78b2c00,0x2bf6a872,0xa913a61f,0xa4a52bd9,0x9e462c00,0x24a5abd9,0xa78b2b64,0x2913aaa7,0x24a52c00,0xaa2faaa7,0x2bf6261f,0xab0e223e,
0x29132c00,0xab0ea23e,0xa4a5ab64,0x2bf62872,0x2b0e2c00,0x1e462872,0xaa2fa61f,0xaba8abd9,0x2bf62c00,0x2ba82bd9,0x2b0e2b64,0x2a2f2aa7,
0xa4a50000,0xaa2f2872,0xabf62b64,0xab0e2bd9,0xa9130000,0xab0e2bd9,0x24a5261f,0x2bf6aaa7,0xab0e0000,0x1e462aa7,0x2a2fab64,0xaba8223e,
0xabf60000,0x2ba8223e,0xab0ea61f,0x2a2f2872,0xaba80000,0x2913a872,0x9e462b64,0xa78babd9,0xaa2f0000,0xa78babd9,0x2ba8261f,0x1e462aa7,
0xa78b0000,0xabf6aaa7,0xa913ab64,0x24a5a23e,0x9e460000,0xa4a5a23e,0xa78ba61f,0xa913a872,0x2b0ea9a8,0x2bf6abd9,0x2a2fab64,0x24a5a872,
0xabf629a8,0xa4a52aa7,0x2b0ea61f,0x2913abd9,0x2ba8a9a8,0xaa2fa23e,0x9e462b64,0x2b0eaaa7,0xaa2f29a8,0x2b0ea872,0xaba8261f,0x2bf6a23e,
0x278ba9a8,0x1e462bd9,0xa913ab64,0x2ba82872,0x9e4629a8,0xaba8aaa7,0x278ba61f,0x2a2f2bd9,0xa4a5a9a8,0x2913223e,0x2bf62b64,0x278b2aa7,
0x291329a8,0x278b2872,0x24a5261f,0x1e46223e,0xa78b29a8,0x1e46223e,0x2913a61f,0x2ba8aaa7,0x1e46a9a8,0xaba82872,0xa78b2b64,0x2a2fa23e,
0x24a529a8,0x2913abd9,0xabf6261f,0x278b2872,0xa913a9a8,0x278b2aa7,0xa4a5ab64,0x1e462bd9,0x2b0e29a8,0xabf6a23e,0x2a2fa61f,0xa4a52aa7,
0xabf6a9a8,0x24a5a872,0x2b0e2b64,0xa913223e,0x2ba829a8,0x2a2f2bd9,0x9e46261f,0xab0ea872,0xaa2fa9a8,0xab0eaaa7,0xaba8ab64,0xabf6abd9,
0xa4a50000,0xaa2fa872,0xabf6ab64,0xab0eabd9,0xa9130000,0xab0eabd9,0x24a5a61f,0x2bf62aa7,0xab0e0000,0x1e46aaa7,0x2a2f2b64,0xaba8a23e,
0xabf60000,0x2ba8a23e,0xab0e261f,0x2a2fa872,0xaba80000,0x29132872,0x9e46ab64,0xa78b2bd9,0xaa2f0000,0xa78b2bd9,0x2ba8a61f,0x1e46aaa7,
0xa78b0000,0xabf62aa7,0xa9132b64,0x24a5223e,0x9e460000,0xa4a5223e,0xa78b261f,0xa9132872,0x2ba82c00,0x29132aa7,0x1e46261f,0xa78ba23e,
0x2a2f2c00,0xa78b223e,0xaba8ab64,0x1e46a872,0x278b2c00,0xabf6a872,0x2913a61f,0x24a52bd9,0x1e462c00,0xa4a5abd9,0x278b2b64,0xa913aaa7,
0xa4a52c00,0x2a2faaa7,0xabf6261f,0x2b0e223e,0xa9132c00,0x2b0ea23e,0x24a5ab64,0xabf62872,0xab0e2c00,0x9e462872,0x2a2fa61f,0x2ba8abd9,
0xabf62c00,0xaba82bd9,0xab0e2b64,0xaa2f2aa7,0xa78ba9a8,0x1e46a23e,0x2913261f,0x2ba82aa7,0x1e4629a8,0xaba8a872,0xa78bab64,0x2a2f223e,
0x24a5a9a8,0x29132bd9,0xabf6a61f,0x278ba872,0xa91329a8,0x278baaa7,0xa4a52b64,0x1e46abd9,0x2b0ea9a8,0xabf6223e,0x2a2f261f,0xa4a5aaa7,
0xabf629a8,0x24a52872,0x2b0eab64,0xa913a23e,0x2ba8a9a8,0x2a2fabd9,0x9e46a61f,0xab0e2872,0xaa2f29a8,0xab0e2aa7,0xaba82b64,0xabf62bd9,
0xab0ea9a8,0xabf6abd9,0xaa2fab64,0xa4a5a872,0x2bf629a8,0x24a52aa7,0xab0ea61f,0xa913abd9,0xaba8a9a8,0x2a2fa23e,0x1e462b64,0xab0eaaa7,
0x2a2f29a8,0xab0ea872,0x2ba8261f,0xabf6a23e,0xa78ba9a8,0x9e462bd9,0x2913ab64,0xaba82872,0x1e4629a8,0x2ba8aaa7,0xa78ba61f,0xaa2f2bd9,
0x24a5a9a8,0xa913223e,0xabf62b64,0xa78b2aa7,0xa91329a8,0xa78b2872,0xa4a5261f,0x9e46223e,0x24a50000,0x2a2fa872,0x2bf6ab64,0x2b0eabd9,
0x29130000,0x2b0eabd9,0xa4a5a61f,0xabf62aa7,0x2b0e0000,0x9e46aaa7,0xaa2f2b64,0x2ba8a23e,0x2bf60000,0xaba8a23e,0x2b0e261f,0xaa2fa872,
0x2ba80000,0xa9132872,0x1e46ab64,0x278b2bd9,0x2a2f0000,0x278b2bd9,0xaba8a61f,0x9e46aaa7,0x278b0000,0x2bf62aa7,0x29132b64,0xa4a5223e,
0x1e460000,0x24a5223e,0x278b261f,0x29132872,0xaba82c00,0xa9132aa7,0x9e46261f,0x278ba23e,0xaa2f2c00,0x278b223e,0x2ba8ab64,0x9e46a872,
0xa78b2c00,0x2bf6a872,0xa913a61f,0xa4a52bd9,0x9e462c00,0x24a5abd9,0xa78b2b64,0x2913aaa7,0x24a52c00,0xaa2faaa7,0x2bf6261f,0xab0e223e,
0x29132c00,0xab0ea23e,0xa4a5ab64,0x2bf62872,0x2b0e2c00,0x1e462872,0xaa2fa61f,0xaba8abd9,0x2bf62c00,0x2ba82bd9,0x2b0e2b64,0x2a2f2aa7,
0x278ba9a8,0x9e46a23e,0xa913261f,0xaba82aa7,0x9e4629a8,0x2ba8a872,0x278bab64,0xaa2f223e,0xa4a5a9a8,0xa9132bd9,0x2bf6a61f,0xa78ba872,
0x291329a8,0xa78baaa7,0x24a52b64,0x9e46abd9,0xab0ea9a8,0x2bf6223e,0xaa2f261f,0x24a5aaa7,0x2bf629a8,0xa4a52872,0xab0eab64,0x2913a23e,
0xaba8a9a8,0xaa2fabd9,0x1e46a61f,0x2b0e2872,0x2a2f29a8,0x2b0e2aa7,0x2ba82b64,0x2bf62bd9,0x2b0ea9a8,0x2bf6abd9,0x2a2fab64,0x24a5a872,
0xabf629a8,0xa4a52aa7,0x2b0ea61f,0x2913abd9,0x2ba8a9a8,0xaa2fa23e,0x9e462b64,0x2b0eaaa7,0xaa2f29a8,0x2b0ea872,0xaba8261f,0x2bf6a23e,
0x278ba9a8,0x1e462bd9,0xa913ab64,0x2ba82872,0x9e4629a8,0xaba8aaa7,0x278ba61f,0x2a2f2bd9,0xa4a5a9a8,0x2913223e,0x2bf62b64,0x278b2aa7,
0x291329a8,0x278b2872,0x24a5261f,0x1e46223e,0xa02fa0f0,0x27b9279c,0x1c16190d,0x27ef27fa,0x9d4d9ed8,0x27e427d1,0x1f2e1da4,0x27cc27e0,
0x985e9b7e,0x27fb27f2,0x211a205a,0x279527b3,0x13a890e9,0x27ff2800,0x229021d7,0x274c2773,0x16939e2c,0x27fd27da,0x273927d8,0xa2e09e51,
0x242120ae,0x26da27a6,0x24c0262c,0xa670a517,0x26df25ab,0x241925a5,0x1c9f2217,0xa7eba766,0x27fe27a9,0x15fd209c,0xa16d9a6b,0xa787a7f6,
0x21bf98c2,0x277727fa,0xa583a102,0xa5cca799,0x279825ca,0x21082585,0xa7fba776,0x18a9a1c5,0x26c327f1,0xa4469bc9,0xa49da6f7,0x268a23e0,
0x1be22449,0xa7f0a6c1,0x20419d7f,0x27b627e2,0x250d15ca,0x263427fe,0xa399a73f,0x270a22c9,0x276727c1,0xa2111fe5,0x25a31c93,0x25ae27eb,
0x9a072424,0xa7f7a6d9,0x271227e9,0xa37d1cd1,0xa7d7a55a,0x9e5da5f3,0x9e1f22e5,0xa7daa738,0x26bb1d41,0x245427e4,0x27df243c,0x1db026ca,
0x234b27ba,0xa71fa029,0x19262657,0xa7f9a4e1,0xa772a1a8,0xa1dca77c,0xa800a57a,0x1084a5d5,0xa060a72c,0x27b22318,0x1b65a544,0x27f22605,
0x27be207e,0x200b27ae,0x9c61263c,0xa7eda503,0x9f7725b7,0xa7c7a59a,0xa679a75c,0x24b4a245,0xa5fba7a2,0x2550a0cc,0x273319a3,0x22fc27f8,
0x27811dee,0x218a27dd,0x950126b2,0xa7fea461,0x27fc224b,0x97c0275b,0xa731a5b9,0x2302a597,0xa67b2078,0xa4b1a7af,0x27c81b01,0x1f6b27f4,
0x2011a69a,0x27bd2485,0xa4d7245e,0xa65fa6b4,0x22ad27f8,0xa745198a,0x94cfa7a1,0x27ff20d2,0x27702400,0xa1e226ed,0x2591a4de,0x25bf2659,
0xa7f99f46,0x193fa7ca,0xa3502680,0xa71da4a9,0x27d2982b,0x1ebf27fc,0x1dbda793,0x27df2126,0xa6fe21a2,0xa3c5a77d,0x1b4c27ff,0xa7f39439,
0x262824cd,0xa51c2666,0x237726e2,0xa7132413,0xa5a0a567,0x25b0a5e6,0xa20ba740,0x2768a2c3,0x250b25f5,0xa6362557,0x2090278c,0xa7ab214f,
0xa469a673,0x26ada4bb,0x9e13a7c5,0x27db9f9c,0x24442588,0xa6c525c8,0xa7e32273,0x9d66a752,0x9890a79a,0x27fba0fc,0x279718db,0xa10e27fa,
0xa28427e1,0xa74e9d8b,0xa581a44c,0x25cfa6c0,0x2651a64c,0x24e824f0,0x203b26f8,0xa7b723db,0x1fcd262e,0xa7c22514,0x1caca7a7,0x27eaa0a8,
0x24c3a7d9,0x266e1e38,0xa6dc26a8,0xa41ea471,0xa7fd238e,0x9661a70d,0x27899a52,0xa16127f6,0x2561221d,0xa5ec2765,0xa167a5a7,0x2788a5a9,
0x987726be,0xa7fb244e,0x27299d97,0xa32427e0,0x27cda614,0x1f222534,0x1d5aa722,0x27e3a340,0xa3f1a26d,0x26f2a753,0xa7f0258a,0x9c0aa5c6,
0xa57e27f2,0xa5d19b97,0x228a23d5,0xa74d26fa,0xa2052735,0xa76922f1,0xa59e27fd,0xa5b2172a,0x2715a17e,0xa3722783,0x251e1566,0xa62627fe,
0x2466a7bf,0x26af9ffd,0x269fa7ec,0x247e1c7a,0xa6381cea,0x2508a7e8,0xa3a49f90,0x2707a7c6,0xa52a2792,0xa61c212c,0xa3569812,0x271ca7fc,
0x21e81d28,0xa76f27e5,0xa80026cd,0xf76a436,0x27f3a65b,0x9b3324dc,0xa3bf26ec,0xa7002403,0x248ba748,0x2696a2a1,0x2459946b,0xa6b727ff,
0xa6cf27d3,0xa4341ea7,0x27e6a7de,0x1d1c1dd5,0xa13124fe,0xa7912640,0x254ba701,0x25ffa3ba,0x21968ead,0xa77f2800,0x149da1ee,0x27ffa76e,
0x26eaa528,0xa406261e,0xa4d920d8,0x265da7a0,0xa7c727f8,0x9f8319bc,0x9cf620c6,0xa7e727a3,0xa6e5276b,0xa40e21ff,0x1c6e0c52,0xa7ec2800,
0xa56c263a,0xa5e22506,0x22b8a084,0xa74327ad,0xa2f62480,0xa734269d,0x2553a463,0xa5f926b0,0xa7fa27ff,0x190d93a8,0xa720274c,0x2345a290,
0xa7e027ef,0x1da49c16,0xa6bc26f0,0x2451a3f6,0xa7b327cc,0x205a9f2e,0xa6482684,0x24f5a4a4,0xa7732795,0x21d7a11a,0xa5c42608,0x258ca542,
0xa76227e9,0x22289cc5,0x25aba421,0x25a5a6da,0xa510266a,0x2632a4c8,0x27a9a6df,0x209ca419,0x9e2c22cf,0x27daa73d,0x27d8a7fe,0x9e5195fd,
0x20ae9693,0x27a6a7fd,0x262ca739,0xa51722e0,0xa61027b6,0x2539a041,0x2334a64f,0xa72524eb,0x1216227f,0x27ffa750,0xa279927b,0xa75127ff,
0x264ea32f,0x24eda726,0xa7b5260e,0xa047253b,0x27cfa7ce,0x9efd9f09,0xa68b27e2,0x249a9d72,0xa4242767,0x26d9a211,0xa7e925a3,0x9cd125ae,
0x255a9a07,0x25f3a7f7,0xa2e52712,0x2738a37d,0x273fa7d7,0xa2c99e5d,0x25e89e1f,0x2565a7da,0x9c93a399,0xa7eb270a,0x26e1a7f5,0xa4169a84,
0x9f3a26fd,0x27cba3ca,0x1d4124f7,0x27e4a646,0x27efa490,0x1c23a693,0x27baa6bb,0xa029a454,0x1406a618,0xa7ff252f,0xa1a8a34b,0xa77c271f,
0xa7fb25c1,0x1844258e,0xa72c2772,0x231821dc,0x19a32679,0x27f8a4b4,0x2718a6d2,0xa367a42e,0x26b2a733,0xa461a2fc,0xa69b978e,0xa48327fc,
0xa7041501,0xa3af27fe,0x9ae82744,0x27f4a2b2,0x8d1b26e7,0x2800a40b,0x276ca661,0xa1faa4d4,0x224b25de,0x275ba571,0xa5b9a2ad,0xa5972745,
0x2078a7fc,0xa7af17c0,0x1b012731,0x27f4a302,0xa69a267b,0x248524b1,0x245ea7c8,0xa6b49f6b,0x27f8a011,0x198aa7bd,0xa7a124d7,0x20d2265f,
0x2547252d,0x2603a61a,0xa313279e,0x272d20e4,0xa29ba6b9,0xa7492456,0x2578a694,0xa5d7a48d,0x1c2f27b1,0x27eea066,0xa6ed24fa,0x24002644,
0x1d34a800,0xa7e59020,0x27caa1e2,0x9f46a770,0x26e22469,0x2413a6ad,0x27eb1e13,0x1c86a7db,0xa740a377,0xa2c32713,0xa7fe99ee,0x959827f7,
0x278c220b,0x214fa768,0x27fd897f,0x96f8a800,0xa7c5a090,0x9f9c27ab,0xa7e81a9d,0x1cde27f5,0x27cf2329,0x1ef0a727,0x9d8ba7fb,0xa7e19890,
0xa7b512df,0x204e27ff,0x24f0274e,0x264ca284,0x25c8a3eb,0xa588a6f4,0xa752a4e8,0xa2732651,0xa0fc26c5,0x279a2444,0x27fa1d66,0x98dba7e3,
0x27f62167,0x9a39a788,0xa70f162f,0x238827fe,0xa473241c,0x26a626dd,0x1e44a66c,0xa7d8a4c5,0xa0a2a7ea,0xa7a89cb8,0x251227c3,0x26309fc0,
0x276425ef,0x2222a55e,0xa800a2da,0x8192273b,0x27531f22,0xa26da7cd,0x25c627e3,0x258a9d5a,0x1b9726f2,0x27f223f1,0xa6fa9c0a,0x23d527f0,
0xa7e0a5d1,0x9d97257e,0x9ee4a74d,0xa7d0a28a,0x2340a324,0xa722a729,0x27fa2540,0x18f4a60a,0x25f71ab6,0xa555a7f5,0x22f1a08a,0xa735a7ac,
0x25e42800,0x256a0b12,0x27832769,0x217ea205,0xa4cf19d5,0x266527f7,0x9ffd2372,0x27bf2715,0xa6d5a7db,0xa4291e07,0xa7e8a6af,0x9cea2466,
0x24038f76,0xa6eca800,0xa7eea758,0x9c3c2256,0x27ff2700,0x146ba3bf,0xa19ca642,0xa77ea4fc,0x230d26b7,0x272e2459,0x25491dc9,0xa601a7de,
0xa4ac9958,0x267f27f9,0x27ca279f,0x1f52a0de,0x1ea79c48,0xa7d3a7ee,0x1dd52406,0x27de26ea,0x26402434,0xa4fea6cf,0xa3ba9d1c,0x270127e6,
0x28002791,0xeada131,0xa76ea5ff,0x21ee254b,0x261e277f,0x25282196,0xa7a0a7ff,0xa0d8149d,0x9acfa005,0xa7f4a7be,0x27062663,0xa3a9a4d2,
0x1dfa1534,0xa7dca7fe,0x27d52782,0x9e82a184,0x236c2143,0xa716a78e,0x27f827fd,0x19bc975c,0x259c24b6,0xa5b4a677,0x276b27c7,0x21ff1f83,
0x23f62345,0x26f02720,0x26552616,0x24e32531,0x24a42451,0x268426bc,0x26c82691,0x243e2492,0x254224f5,0x26082648,0x272a26fb,0x231e23d0,
0x25d3258c,0x257c25c4,0x277b2755,0x21ae2268,0xa5f1a476,0xa55ca6a4,0xa15ba46e,0x278a26a9,0xa7c4a710,0x9fb4a383,0x1cc59a20,0x27e927f7,
0xa7c1a800,0x1fd904b6,0x24c82228,0x266a2762,0xa5eaa70c,0x25632393,0x273d2632,0x22cf2510,0x27502539,0x227f2610,0xa7ffa725,0x927ba334,
0x272627ff,0xa32f9216,0xa53ba751,0x260e2279,0x1f0924ed,0xa7cea64e,0x1d72a047,0x27e227b5,0xa4eb9efd,0xa64fa7cf,0x26f5249a,0x23e6268b,
0xa7f5a5e8,0x9a84a565,0xa0962173,0xa7aaa786,0xa22ea6e1,0x27612416,0xa800a668,0x87dba4ca,0x262a1fa8,0x251927c5,0xa0b4a672,0x27a624be,
0x26ab27fd,0xa46b16c5,0x26a22155,0x2478278b,0x27d12682,0x9ecc24a7,0x269327cb,0xa4901f3a,0xa0ea23fb,0xa79da6ef,0xa52f1c23,0xa618a7ef,
0xa756a74b,0x2262a296,0xa58ea7ff,0x25c19406,0x23caa120,0x26fd2794,0x26461844,0x24f727fb,0xa6e7a704,0x240ba3af,0x26619ae8,0x24d427f4,
0x26d28d1b,0x242e2800,0x1d03276c,0xa7e7a1fa,0x178e2718,0xa7fca367,0xa78fa622,0x213da523,0xa744a69b,0x22b2a483,0x25e09e8e,0x256e27d5,
0x254e276d,0xa5fd21f4,0xa137a800,0x27900de4,0xa7e6a3b4,0x1d0fa703,0x26d0263e,0xa4312501,0x26e99de2,0x240927dd,0xa7ed9e9b,0x9c55a7d4,
0xa1902620,0xa780a525,0x2571a361,0x25de2719,0xa25ca7ba,0x2757a023,0xa8009c2f,0x9020a7ee,0x252d26cb,0xa61a2439,0x279e9d34,0x20e427e5,
0xa6b9a547,0x2456a603,0xa6942313,0xa48da72d,0x27b1229b,0xa0662749,0x24faa578,0x264425d7,0x19ee27eb,0xa7f71c86,0xa0ba27c0,0xa7a59ff1,
0x97fa7fe,0x28009598,0x2234a785,0x27602179,0x9a9d27fd,0xa7f596f8,0xa39e2737,0xa709a2eb,0x1e69a7e8,0x27d61cde,0x247ba6d7,0x26a12426,
0x1f15a7ff,0x27cd91b2,0x268821cb,0xa49f2775,0xa53d2723,0xa60ca33a,0xa329a612,0x2727a536,0x2778a497,0x21b9268d,0x92df27cf,0xa7ff1ef0,
0xa7f01bb0,0x1bfba7f1,0x23eba7b5,0x26f4204e,0xa41c27f6,0xa6dd9a39,0x266ca70f,0x24c52388,0x27eaa473,0x1cb826a6,0xa7c31e44,0x1fc0a7d8,
0xa5efa0a2,0x255ea7a8,0x22da2512,0xa73b2630,0x962f2764,0xa7fe2222,0x22d4a800,0x273c8192,0x260aa7d0,0x25401ee4,0xa114a495,0x2796a68f,
0xa6c618f4,0x2441a7fa,0xa686279b,0xa4a2a0f6,0xa0352774,0xa7b821d1,0x2653114d,0xa4e62800,0x27ffa4f2,0x1344264a,0x21b3a7b4,0x277aa054,
0xa75f278d,0xa23aa149,0xa80025f7,0x8b12a555,0x20c022be,0xa7a42741,0x99d525e4,0xa7f7256a,0x27d6a6e4,0x1e762411,0x27dba4cf,0x9e072665,
0x9ab6a4b9,0x27f5a675,0x208aa6d5,0x27aca429,0x27f9a72e,0x1958230d,0xa0de2601,0xa79f2549,0x2256a67f,0x2758a4ac,0x25939f52,0xa5bd27ca,
0xa4fc1c3c,0x2642a7ee,0x27b0a7bb,0x206c201d,0xa7de277e,0x9dc9a19c,0x1eb3a575,0x27d3a5d9,0xa7c926b6,0x1f5fa45c,0x267da488,0xa4ae2698,
0xa73027f3,0xa3071b1a,0x27fca7af,0x17f22072,0xa2a72595,0xa74725bb,0x25dba75a,0x2573a251,0x20171971,0xa7bc27f9,0x1c48a35c,0x27eea71b,
0x26d4a624,0xa42c2521,0x2677a716,0x24b6a36c,0x27bea75d,0xa005223f,0x24d2a5b4,0x2663a59c,0x27fea7f4,0x15341acf,0x2184a3a9,0x2782a706,
0x278ea7dc,0x21439dfa,0x175c9e82,0x27fda7d5,0xa531257c,0x2616a5d3,0xa0f021ae,0x279ca77b,0xa49224e3,0x2691a655,0x9ed8202f,0x27d1a7b9,
0xa3d0243e,0x26fba6c8,0x9b7e1d4d,0x27f2a7e4,0xa268231e,0x2755a72a,0x90e9185e,0x2800a7fb,0x2217a4c0,0xa7662670,0xa80027c4,0x4b61fb4,
0x9a6b9c9f,0xa7f627eb,0xa70c27c1,0x23939fd9,0xa476216d,0xa6a42787,0xa46e25ea,0x26a9a563,0xa71025f1,0xa383255c,0x9a20215b,0x27f7a78a,
0x98c223e6,0x27faa6f5,0xa1029be2,0xa79927f0,0x25caa1bf,0x2585a777,0xa7762583,0xa1c525cc,0x27f1a798,0x9bc9a108,0xa6f727fb,0x23e098a9,
0x2449a6c3,0xa6c12446,0x9d7f249d,0x27e2a68a,0x9fa8a22e,0xa7c52761,0x2672a800,0xa4be87db,0xa7fd262a,0x96c52519,0xa155a0b4,0xa78b27a6,
0xa17326ab,0x2786a46b,0xa7fe26a2,0x15ca2478,0x2668a096,0x24caa7aa,0x9fe52634,0x27c1a50d,0x243c2060,0x26caa7b2,0x26829b65,0x24a7a7f2,
0x2657a7df,0xa4e19db0,0x23fba7d1,0xa6ef1ecc,0xa57a9926,0xa5d527f9,0xa74b20ea,0xa296279d,0xa5442800,0x26059084,0xa1202756,0x2794a262,
0xa6229d03,0xa52327e7,0xa0cc27c7,0x27a29f77,0x9e8e278f,0x27d5a13d,0x27dda550,0x9deea5fb,0x27aea5e0,0xa07ea56e,0xa503a18a,0xa63c2781,
0xa59aa00b,0xa5b727be,0xa24527ed,0x275c9c61,0x276d14cf,0x21f4a7ff,0xa8002190,0xde42780,0xa3b4a54e,0xa70325fd,0x263e2137,0x2501a790,
0x9de227e6,0x27dd9d0f,0x9e9ba6d0,0xa7d42431,0x2620a6e9,0xa525a409,0xa36127ed,0x27191c55,0xa7fc193f,0x982b27f9,0xa126a71d,0xa7932350,
0x277d1ebf,0x21a2a7d2,0x143927df,0x27ff9dbd,0xa659a3c5,0xa4de26fe,0x2023a7f3,0xa7ba9b4c,0x24a925bf,0x2680a591,0xa4392757,0x26cb225c,
0x27c09e69,0x9ff1a7d6,0x2666a47b,0xa4cda6a1,0xa78520ba,0x217927a5,0xa5e6251c,0x25672628,0x2737a234,0xa2eba760,0x2557a5b0,0xa5f5a5a0,
0xa6d7239e,0x24262709,0xa4bb2636,0x2673250b,0xa6c0210e,0x244c2797,0x268d260c,0x2497a53d,0x23dba5cf,0xa6f8a581,0xa7f1a1b9,0x9bb02778,
0x91b227b7,0x27ff203b,0x27759bfb,0xa1cba7f0,0xa33aa7cd,0xa7231f15,0xa536249f,0x26122688,0x2514a2d4,0xa62ea73c,0xa0a825ec,0x27a72561,
0x1e3827c2,0x27d91fcd,0xa471a7ea,0xa6a81cac,0xa70da66e,0xa38e24c3,0x27f6241e,0x1a52a6dc,0x27651661,0xa21da7fd,0xa5a92161,0x25a72789,
0xa1d12441,0x277426c6,0xa800a4a2,0x114d2686,0xa64aa7b8,0xa4f22035,0x2054a4e6,0xa7b4a653,0x268f1344,0xa495a7ff,0x26be277a,0x244ea1b3,
0x20f62796,0x279b2114,0xa6141877,0x253427fb,0x172aa508,0xa7fda638,0xa149a707,0xa78da3a4,0x27fe25b2,0x9566a59e,0x2741223a,0xa2bea75f,
0x1c7a2626,0x27ec251e,0x241127a4,0x26e420c0,0xa7c6a47e,0x1f90269f,0xa6759e76,0x24b927d6,0x201d25bd,0x27bb2593,0x265b21e8,0xa4dca76f,
0xa5d9a06c,0x257527b0,0x274827f3,0x22a19b33,0xa792a7d3,0xa12c1eb3,0x1812248b,0x27fc2696,0x9d28a52a,0xa7e5a61c,0xa6cda356,0x2436271c,
0xa45ca65d,0xa6b6a4d9,0x269827bc,0x24882017,0x1b1a9f5f,0xa7f3a7c9,0x207224ae,0x27af267d,0x25bb2307,0xa595a730,0xa25197f2,0x275a27fc,
0x27f92747,0x9971a2a7,0xa71ba573,0x235c25db,0x263a26e5,0x2506240e,0xa0849c6e,0x27ad27ec,0x2480256c,0x269d25e2,0xa463a2b8,0x26b02743,
0x20c622f6,0x27a32734,0xa624a553,0x252125f9,0xc521cf6,0x280027e7,0xa75da6d4,0x223f242c,
};

#define PROF(slot) do {} while (0)
#define PROF3(slot) do {} while (0)
#define PROF2(slot) do {} while (0)

__device__ __forceinline__ uint32_t smem_u32(const void* p) { return (uint32_t)__cvta_generic_to_shared(p); }

__device__ __forceinline__ void mbar_init(uint32_t a, uint32_t c) {
  asm volatile("mbarrier.init.shared::cta.b64 [%0], %1;\n" ::"r"(a), "r"(c) : "memory");
}
__device__ __forceinline__ void mbar_expect_tx(uint32_t a, uint32_t bytes) {
  asm volatile("mbarrier.arrive.expect_tx.shared::cta.b64 _, [%0], %1;\n" ::"r"(a), "r"(bytes) : "memory");
}
__device__ __forceinline__ void mbar_arrive_cluster(uint32_t cluster_addr) {
  asm volatile("mbarrier.arrive.shared::cluster.b64 _, [%0];\n" ::"r"(cluster_addr) : "memory");
}
__device__ __forceinline__ void mbar_arrive_cluster_n(uint32_t cluster_addr, uint32_t n) {
  asm volatile("mbarrier.arrive.shared::cluster.b64 _, [%0], %1;\n" ::"r"(cluster_addr), "r"(n) : "memory");
}
__device__ __forceinline__ bool mbar_try(uint32_t a, uint32_t parity) {
  uint32_t ok;
  asm volatile("{\n.reg .pred p;\nmbarrier.try_wait.parity.shared::cta.b64 p, [%1], %2;\nselp.u32 %0, 1, 0, p;\n}\n"
               : "=r"(ok) : "r"(a), "r"(parity) : "memory");
  return ok;
}
__device__ __forceinline__ void mbar_wait(uint32_t a, uint32_t parity) {
  if (mbar_try(a, parity)) return;
#pragma unroll 1
  for (int n = 0; n < SPIN_LIMIT; n++)
    if (mbar_try(a, parity)) break;
}
__device__ __forceinline__ void mbar_wait_idle(uint32_t a, uint32_t parity) {
#pragma unroll 1
  for (int n = 0; n < SPIN_LIMIT; n++) {
    uint32_t ok;
    asm volatile("{\n.reg .pred p;\nmbarrier.try_wait.parity.shared::cta.b64 p, [%1], %2, %3;\nselp.u32 %0, 1, 0, p;\n}\n"
                 : "=r"(ok) : "r"(a), "r"(parity), "r"(4000) : "memory");
    if (ok) break;
  }
}
__device__ __forceinline__ bool elect_one() {
  uint32_t p;
  asm volatile("{\n.reg .pred P;\nelect.sync _|P, 0xffffffff;\nselp.u32 %0, 1, 0, P;\n}\n" : "=r"(p));
  return p;
}
__device__ __forceinline__ uint32_t mapa(uint32_t a, uint32_t rank) {
  uint32_t r;
  asm volatile("mapa.shared::cluster.u32 %0, %1, %2;\n" : "=r"(r) : "r"(a), "r"(rank));
  return r;
}
__device__ __forceinline__ void nb_sync(int id, int n) { asm volatile("bar.sync %0, %1;\n" ::"r"(id), "r"(n) : "memory"); }
__device__ __forceinline__ void nb_arrive(int id, int n) { asm volatile("bar.arrive %0, %1;\n" ::"r"(id), "r"(n) : "memory"); }
__device__ __forceinline__ void cluster_sync_all() {
  asm volatile("barrier.cluster.arrive.relaxed.aligned;\nbarrier.cluster.wait.aligned;\n" ::: "memory");
}
__device__ __forceinline__ void fence_async_smem() { asm volatile("fence.proxy.async.shared::cta;\n" ::: "memory"); }
__device__ __forceinline__ void fence_async_all() { asm volatile("fence.proxy.async.global;\n" ::: "memory"); }

__device__ __forceinline__ void tma_load_3d(uint32_t dst, const CUtensorMap* tm, uint32_t bar, int c0, int c1, int c2) {
  asm volatile(
      "cp.async.bulk.tensor.3d.shared::cluster.global.mbarrier::complete_tx::bytes [%0], [%1, {%3, %4, %5}], [%2];\n"
      ::"r"(dst), "l"(tm), "r"(bar), "r"(c0), "r"(c1), "r"(c2) : "memory");
}
__device__ __forceinline__ void tma_load_4d(uint32_t dst, const CUtensorMap* tm, uint32_t bar, int c0, int c1, int c2, int c3) {
  asm volatile(
      "cp.async.bulk.tensor.4d.shared::cluster.global.mbarrier::complete_tx::bytes [%0], [%1, {%3, %4, %5, %6}], [%2];\n"
      ::"r"(dst), "l"(tm), "r"(bar), "r"(c0), "r"(c1), "r"(c2), "r"(c3) : "memory");
}
__device__ __forceinline__ void tma_load_3d_mc(uint32_t dst, const CUtensorMap* tm, uint32_t bar, int c0, int c1, int c2) {
  asm volatile(
      "cp.async.bulk.tensor.3d.shared::cluster.global.mbarrier::complete_tx::bytes.multicast::cluster [%0], [%1, {%3, %4, %5}], [%2], %6;\n"
      ::"r"(dst), "l"(tm), "r"(bar), "r"(c0), "r"(c1), "r"(c2), "h"((uint16_t)3) : "memory");
}
__device__ __forceinline__ void tma_load_5d(uint32_t dst, const CUtensorMap* tm, uint32_t bar, int c0, int c4) {
  asm volatile(
      "cp.async.bulk.tensor.5d.shared::cluster.global.mbarrier::complete_tx::bytes [%0], [%1, {%3, %5, %5, %5, %4}], [%2];\n"
      ::"r"(dst), "l"(tm), "r"(bar), "r"(c0), "r"(c4), "r"(0) : "memory");
}
__device__ __forceinline__ void bulk_load(uint32_t dst, const void* src, uint32_t bytes, uint32_t bar) {
  asm volatile("cp.async.bulk.shared::cluster.global.mbarrier::complete_tx::bytes [%0], [%1], %2, [%3];\n"
               ::"r"(dst), "l"(src), "r"(bytes), "r"(bar) : "memory");
}
__device__ __forceinline__ void bulk_commit() { asm volatile("cp.async.bulk.commit_group;\n" ::: "memory"); }
__device__ __forceinline__ void bulk_wait0() { asm volatile("cp.async.bulk.wait_group 0;\n" ::: "memory"); }
__device__ __forceinline__ void prefetch_tmap(const CUtensorMap* tm) {
  asm volatile("prefetch.tensormap [%0];\n" ::"l"(tm) : "memory");
}

__device__ __forceinline__ void wg_fence() { asm volatile("wgmma.fence.sync.aligned;\n" ::: "memory"); }
__device__ __forceinline__ void wg_commit() { asm volatile("wgmma.commit_group.sync.aligned;\n" ::: "memory"); }
template <int N> __device__ __forceinline__ void wg_wait() {
  asm volatile("wgmma.wait_group.sync.aligned %0;\n" ::"n"(N) : "memory");
}
__device__ __forceinline__ uint64_t mkdesc(uint32_t addr, uint32_t lbo, uint32_t sbo, uint32_t swz) {
  return (uint64_t)((addr & 0x3FFFF) >> 4) | ((uint64_t)(lbo >> 4) << 16) | ((uint64_t)(sbo >> 4) << 32) |
         ((uint64_t)swz << 62);
}

#define R4(d, o) "+f"(d[o + 0]), "+f"(d[o + 1]), "+f"(d[o + 2]), "+f"(d[o + 3])
#define R8(d, o) R4(d, o), R4(d, o + 4)
#define R16(d, o) R8(d, o), R8(d, o + 8)
#define R32(d, o) R16(d, o), R16(d, o + 16)
#define R64(d, o) R32(d, o), R32(d, o + 32)

__device__ __forceinline__ void wgmma_n192(float (&d)[96], uint64_t da, uint64_t db, uint32_t acc) {
  asm volatile(
      "{\n.reg .pred p;\nsetp.ne.u32 p, %98, 0;\n"
      "wgmma.mma_async.sync.aligned.m64n192k16.f32.bf16.bf16 "
      "{%0,%1,%2,%3,%4,%5,%6,%7,%8,%9,%10,%11,%12,%13,%14,%15,%16,%17,%18,%19,%20,%21,%22,%23,%24,%25,%26,%27,%28,%29,%30,%31,"
      "%32,%33,%34,%35,%36,%37,%38,%39,%40,%41,%42,%43,%44,%45,%46,%47,%48,%49,%50,%51,%52,%53,%54,%55,%56,%57,%58,%59,%60,%61,%62,%63,"
      "%64,%65,%66,%67,%68,%69,%70,%71,%72,%73,%74,%75,%76,%77,%78,%79,%80,%81,%82,%83,%84,%85,%86,%87,%88,%89,%90,%91,%92,%93,%94,%95}, "
      "%96, %97, p, 1, 1, 0, 1;\n}\n"
      : R64(d, 0), R32(d, 64)
      : "l"(da), "l"(db), "r"(acc));
}
__device__ __forceinline__ void wgmma_n128(float (&d)[64], uint64_t da, uint64_t db, uint32_t acc) {
  asm volatile(
      "{\n.reg .pred p;\nsetp.ne.u32 p, %66, 0;\n"
      "wgmma.mma_async.sync.aligned.m64n128k16.f32.bf16.bf16 "
      "{%0,%1,%2,%3,%4,%5,%6,%7,%8,%9,%10,%11,%12,%13,%14,%15,%16,%17,%18,%19,%20,%21,%22,%23,%24,%25,%26,%27,%28,%29,%30,%31,"
      "%32,%33,%34,%35,%36,%37,%38,%39,%40,%41,%42,%43,%44,%45,%46,%47,%48,%49,%50,%51,%52,%53,%54,%55,%56,%57,%58,%59,%60,%61,%62,%63}, "
      "%64, %65, p, 1, 1, 0, 1;\n}\n"
      : R64(d, 0)
      : "l"(da), "l"(db), "r"(acc));
}
template <int N> __device__ __forceinline__ void fence_regs(float (&d)[N]) {
#pragma unroll
  for (int i = 0; i < N; i++) asm volatile("" : "+f"(d[i])::"memory");
}

__device__ __forceinline__ void mma16816(float (&d)[4], uint32_t a0, uint32_t a1, uint32_t a2, uint32_t a3, uint32_t b0,
                                         uint32_t b1) {
  asm("mma.sync.aligned.m16n8k16.row.col.f32.bf16.bf16.f32 {%0,%1,%2,%3}, {%4,%5,%6,%7}, {%8,%9}, {%0,%1,%2,%3};\n"
      : "+f"(d[0]), "+f"(d[1]), "+f"(d[2]), "+f"(d[3])
      : "r"(a0), "r"(a1), "r"(a2), "r"(a3), "r"(b0), "r"(b1));
}
__device__ __forceinline__ void mma16816_z(float (&d)[4], uint32_t a0, uint32_t a1, uint32_t a2, uint32_t a3, uint32_t b0,
                                           uint32_t b1) {
  asm("mma.sync.aligned.m16n8k16.row.col.f32.bf16.bf16.f32 {%0,%1,%2,%3}, {%4,%5,%6,%7}, {%8,%9}, {%10,%10,%10,%10};\n"
      : "=f"(d[0]), "=f"(d[1]), "=f"(d[2]), "=f"(d[3])
      : "r"(a0), "r"(a1), "r"(a2), "r"(a3), "r"(b0), "r"(b1), "f"(0.f));
}
__device__ __forceinline__ void ldsm4t(uint32_t (&r)[4], uint32_t a) {
  asm volatile("ldmatrix.sync.aligned.m8n8.x4.trans.shared.b16 {%0,%1,%2,%3}, [%4];\n"
               : "=r"(r[0]), "=r"(r[1]), "=r"(r[2]), "=r"(r[3]) : "r"(a) : "memory");
}
__device__ __forceinline__ void ldsm2t(uint32_t& r0, uint32_t& r1, uint32_t a) {
  asm volatile("ldmatrix.sync.aligned.m8n8.x2.trans.shared.b16 {%0,%1}, [%2];\n" : "=r"(r0), "=r"(r1) : "r"(a) : "memory");
}
__device__ __forceinline__ void st_async128(uint32_t a, uint32_t bar, uint32_t x, uint32_t y, uint32_t z, uint32_t w) {
  asm volatile("st.async.weak.shared::cluster.mbarrier::complete_tx::bytes.v4.b32 [%0], {%2,%3,%4,%5}, [%1];\n"
               ::"r"(a), "r"(bar), "r"(x), "r"(y), "r"(z), "r"(w) : "memory");
}
__device__ __forceinline__ void mbar_arrive(uint32_t a) {
  asm volatile("mbarrier.arrive.shared::cta.b64 _, [%0];\n" ::"r"(a) : "memory");
}
__device__ __forceinline__ void stsm4(uint32_t a, uint32_t r0, uint32_t r1, uint32_t r2, uint32_t r3) {
  asm volatile("stmatrix.sync.aligned.m8n8.x4.shared.b16 [%0], {%1,%2,%3,%4};\n"
               ::"r"(a), "r"(r0), "r"(r1), "r"(r2), "r"(r3) : "memory");
}
__device__ __forceinline__ void stsm4t(uint32_t a, uint32_t r0, uint32_t r1, uint32_t r2, uint32_t r3) {
  asm volatile("stmatrix.sync.aligned.m8n8.x4.trans.shared.b16 [%0], {%1,%2,%3,%4};\n"
               ::"r"(a), "r"(r0), "r"(r1), "r"(r2), "r"(r3) : "memory");
}
__device__ __forceinline__ uint2 lds64(uint32_t a) {
  uint2 v;
  asm volatile("ld.shared.v2.u32 {%0,%1}, [%2];\n" : "=r"(v.x), "=r"(v.y) : "r"(a));
  return v;
}
__device__ __forceinline__ uint4 lds128(uint32_t a) {
  uint4 v;
  asm volatile("ld.shared.v4.u32 {%0,%1,%2,%3}, [%4];\n" : "=r"(v.x), "=r"(v.y), "=r"(v.z), "=r"(v.w) : "r"(a) : "memory");
  return v;
}
__device__ __forceinline__ void sts128(uint32_t a, uint32_t x, uint32_t y, uint32_t z, uint32_t w) {
  asm volatile("st.shared.v4.u32 [%0], {%1,%2,%3,%4};\n" ::"r"(a), "r"(x), "r"(y), "r"(z), "r"(w) : "memory");
}
__device__ __forceinline__ uint32_t pack_bf16(float lo, float hi) {
  uint32_t r;
  asm("cvt.rn.bf16x2.f32 %0, %1, %2;\n" : "=r"(r) : "f"(hi), "f"(lo));
  return r;
}
__device__ __forceinline__ uint32_t bmul2(uint32_t a, uint32_t b) {
  uint32_t r;
  asm("mul.rn.bf16x2 %0, %1, %2;\n" : "=r"(r) : "r"(a), "r"(b));
  return r;
}
__device__ __forceinline__ uint32_t bmax2(uint32_t a, uint32_t b) {
  uint32_t r;
  asm("max.bf16x2 %0, %1, %2;\n" : "=r"(r) : "r"(a), "r"(b));
  return r;
}
__device__ __forceinline__ uint32_t bfma2(uint32_t a, uint32_t b, uint32_t c) {
  uint32_t r;
  asm("fma.rn.bf16x2 %0, %1, %2, %3;\n" : "=r"(r) : "r"(a), "r"(b), "r"(c));
  return r;
}
__device__ __forceinline__ void prefetch_l2(const void* p) { asm volatile("prefetch.global.L2 [%0];\n" ::"l"(p)); }
__device__ __forceinline__ void cp_async16n(uint32_t dst, const void* src) {
  asm volatile("cp.async.cg.shared.global [%0], [%1], 16;\n" ::"r"(dst), "l"(src) : "memory");
}
__device__ __forceinline__ void cp_async16(uint32_t dst, const void* src, uint32_t srcbytes) {
  asm volatile("cp.async.cg.shared.global.L2::256B [%0], [%1], 16, %2;\n" ::"r"(dst), "l"(src), "r"(srcbytes) : "memory");
}
__device__ __forceinline__ uint32_t ld_acquire(const uint32_t* p) {
  uint32_t v;
  asm volatile("ld.acquire.gpu.global.u32 %0, [%1];\n" : "=r"(v) : "l"(p) : "memory");
  return v;
}
__device__ __forceinline__ uint32_t ld_relaxed(const uint32_t* p) {
  uint32_t v;
  asm volatile("ld.relaxed.gpu.global.u32 %0, [%1];\n" : "=r"(v) : "l"(p) : "memory");
  return v;
}
__device__ __forceinline__ void st_release(uint32_t* p, uint32_t v) {
  asm volatile("st.release.gpu.global.u32 [%0], %1;\n" ::"l"(p), "r"(v) : "memory");
}
__device__ __forceinline__ void wait_flag(const uint32_t* p, uint32_t want) {
  int n = 0;
  while (ld_relaxed(p) != want && ++n < SPIN_LIMIT) __nanosleep(40);
  (void)ld_acquire(p);
}

struct Params {
  const __nv_bfloat16* x;
  const __nv_bfloat16* w;
  const __nv_bfloat16* q;
  const __nv_bfloat16* k;
  const __nv_bfloat16* v;
  const __nv_bfloat16* shift_k;
  const __nv_bfloat16* ssm_k;
  const __nv_bfloat16* ssm_D;
  const __nv_bfloat16* wo;
  __nv_bfloat16* out;
};

#define U4(c, d, o) c(d[o + 0]), c(d[o + 1]), c(d[o + 2]), c(d[o + 3])
#define U8(c, d, o) U4(c, d, o), U4(c, d, o + 4)
#define U16(c, d, o) U8(c, d, o), U8(c, d, o + 8)
#define U32(c, d, o) U16(c, d, o), U16(c, d, o + 16)
#define D32 "{%0,%1,%2,%3,%4,%5,%6,%7,%8,%9,%10,%11,%12,%13,%14,%15,%16,%17,%18,%19,%20,%21,%22,%23,%24,%25,%26,%27,%28,%29,%30,%31}"
#define D16 "{%0,%1,%2,%3,%4,%5,%6,%7,%8,%9,%10,%11,%12,%13,%14,%15}"
#define D8 "{%0,%1,%2,%3,%4,%5,%6,%7}"
template <int ACC> __device__ __forceinline__ void hmma_n128t(uint32_t (&d)[32], const uint32_t (&a)[4], uint64_t db) {
  if (ACC)
    asm volatile("wgmma.mma_async.sync.aligned.m64n128k16.f16.f16.f16 " D32 ", {%32,%33,%34,%35}, %36, 1, 1, 1, 1;\n"
                 : U32("+r", d, 0) : "r"(a[0]), "r"(a[1]), "r"(a[2]), "r"(a[3]), "l"(db));
  else
    asm volatile("wgmma.mma_async.sync.aligned.m64n128k16.f16.f16.f16 " D32 ", {%32,%33,%34,%35}, %36, 0, 1, 1, 1;\n"
                 : U32("=r", d, 0) : "r"(a[0]), "r"(a[1]), "r"(a[2]), "r"(a[3]), "l"(db));
}
template <int ACC, int TB> __device__ __forceinline__ void hmma_n32(uint32_t (&d)[8], const uint32_t (&a)[4], uint64_t db) {
  if (ACC)
    asm volatile("wgmma.mma_async.sync.aligned.m64n32k16.f16.f16.f16 " D8 ", {%8,%9,%10,%11}, %12, 1, 1, 1, %13;\n"
                 : U8("+r", d, 0) : "r"(a[0]), "r"(a[1]), "r"(a[2]), "r"(a[3]), "l"(db), "n"(TB));
  else
    asm volatile("wgmma.mma_async.sync.aligned.m64n32k16.f16.f16.f16 " D8 ", {%8,%9,%10,%11}, %12, 0, 1, 1, %13;\n"
                 : U8("=r", d, 0) : "r"(a[0]), "r"(a[1]), "r"(a[2]), "r"(a[3]), "l"(db), "n"(TB));
}
template <int ACC> __device__ __forceinline__ void hmma_n64t(uint32_t (&d)[16], const uint32_t (&a)[4], uint64_t db) {
  if (ACC)
    asm volatile("wgmma.mma_async.sync.aligned.m64n64k16.f16.f16.f16 " D16 ", {%16,%17,%18,%19}, %20, 1, 1, 1, 1;\n"
                 : U16("+r", d, 0) : "r"(a[0]), "r"(a[1]), "r"(a[2]), "r"(a[3]), "l"(db));
  else
    asm volatile("wgmma.mma_async.sync.aligned.m64n64k16.f16.f16.f16 " D16 ", {%16,%17,%18,%19}, %20, 0, 1, 1, 1;\n"
                 : U16("=r", d, 0) : "r"(a[0]), "r"(a[1]), "r"(a[2]), "r"(a[3]), "l"(db));
}
template <int N> __device__ __forceinline__ void fence_regs(uint32_t (&d)[N]) {
#pragma unroll
  for (int i = 0; i < N; i++) asm volatile("" : "+r"(d[i])::"memory");
}
__device__ __forceinline__ uint32_t hmul(uint32_t a, uint32_t b) { uint32_t r; asm("mul.rn.f16x2 %0, %1, %2;\n" : "=r"(r) : "r"(a), "r"(b)); return r; }
__device__ __forceinline__ uint32_t hfma(uint32_t a, uint32_t b, uint32_t c) { uint32_t r; asm("fma.rn.f16x2 %0, %1, %2, %3;\n" : "=r"(r) : "r"(a), "r"(b), "r"(c)); return r; }
__device__ __forceinline__ uint32_t hfnma(uint32_t a, uint32_t b, uint32_t c) {
  uint32_t r;
  asm("{\n.reg .b32 t;\nneg.f16x2 t, %1;\nfma.rn.f16x2 %0, t, %2, %3;\n}\n" : "=r"(r) : "r"(a), "r"(b), "r"(c));
  return r;
}
__device__ __forceinline__ void rot(uint32_t xr, uint32_t xi, uint32_t t, uint32_t s, uint32_t& pr, uint32_t& pi) {
  const uint32_t a = hfma(xi, t, xr);
  pi = hfma(a, s, xi);
  pr = hfma(pi, t, a);
}
template <int BH> __device__ __forceinline__ void fft_e1(const uint32_t (&d)[32], const uint32_t (&tw)[12], uint32_t (&a2)[2][2][4]) {
#pragma unroll
  for (int be = 0; be < 2; be++)
#pragma unroll
    for (int s = 0; s < 2; s++) {
      const int o = 16 * s + 8 * be + 2 * BH, p = 4 * BH;
      uint32_t pr, pi;
      rot(d[o], d[o + 1], tw[p], tw[p + 1], pr, pi);
      const uint32_t qr = hfnma(d[o + 5], tw[p + 2], d[o + 4]), qi = hfma(d[o + 4], tw[p + 2], d[o + 5]);
      a2[be][0][s] = hfma(qi, tw[p + 3], pr);
      a2[be][0][2 + s] = hfnma(qr, tw[p + 3], pi);
      a2[be][1][s] = hfnma(qi, tw[p + 3], pr);
      a2[be][1][2 + s] = hfma(qr, tw[p + 3], pi);
    }
}
__device__ __forceinline__ uint32_t hfms(uint32_t a, uint32_t b, uint32_t c) {
  uint32_t r;
  asm("{\n.reg .b32 t;\nneg.f16x2 t, %3;\nfma.rn.f16x2 %0, %1, %2, t;\n}\n" : "=r"(r) : "r"(a), "r"(b), "r"(c));
  return r;
}
__device__ __forceinline__ void fft_e2(const uint32_t (&d0)[8], const uint32_t (&d1)[8], uint32_t (&a3)[2][4]) {
#pragma unroll
  for (int j = 0; j < 2; j++) {
    const uint32_t ur = d0[2 * j], ui = d0[4 + 2 * j], hr = d0[2 * j + 1], hi = d0[5 + 2 * j];
    const uint32_t vr = d1[2 * j], vi = d1[4 + 2 * j], gr = d1[2 * j + 1], gi = d1[5 + 2 * j];
    const uint32_t pr = hfnma(ui, hi, hmul(ur, hr)), pi = hfma(ui, hr, hmul(ur, hi));
    a3[j][0] = pr;
    a3[j][2] = pi;
    a3[j][1] = hfnma(vi, hi, hfma(vr, hr, hfnma(ui, gi, hfms(ur, gr, pi))));
    a3[j][3] = hfma(vi, hr, hfma(vr, hi, hfma(ui, gr, hfma(ur, gi, pr))));
  }
}
__device__ __forceinline__ void fft_e3(const uint32_t (&d)[2][8], const uint32_t (&tw)[12], uint32_t zaddr) {
#pragma unroll
  for (int c = 0; c < 2; c++) {
    uint32_t zr[4], zi[4];
#pragma unroll
    for (int nb = 0; nb < 4; nb++) {
      const int i = 4 * (nb & 1) + (nb >> 1);
      rot(d[c][i], d[c][i + 2], tw[8 + 2 * (nb & 1)], tw[9 + 2 * (nb & 1)], zr[nb], zi[nb]);
    }
    stsm4(zaddr + c * 2048, zr[0], zr[1], zr[2], zr[3]);
    stsm4(zaddr + c * 2048 + 1024, zi[0], zi[1], zi[2], zi[3]);
  }
}
__device__ __forceinline__ float bf_lo(uint32_t v) {
  uint32_t r;
  asm("prmt.b32 %0, %1, 0, 0x1044;\n" : "=r"(r) : "r"(v));
  return __uint_as_float(r);
}
__device__ __forceinline__ float bf_hi(uint32_t v) { return __uint_as_float(v & 0xffff0000u); }
__device__ __forceinline__ float ex2(float x) {
  float r;
  asm("ex2.approx.ftz.f32 %0, %1;\n" : "=f"(r) : "f"(x));
  return r;
}
__device__ __forceinline__ float rcp(float x) {
  float r;
  asm("rcp.approx.ftz.f32 %0, %1;\n" : "=f"(r) : "f"(x));
  return r;
}

__device__ __forceinline__ int g2_a(int s, int h) { return (((0xA1023 ^ (h * 0x11)) >> (4 * s)) & 15) * 16384; }
__device__ __forceinline__ int g2_b(int s) { return (((11 | 13 << 5 | 22 << 10 | 26 << 15 | 24 << 20) >> (5 * s)) & 31) * 8192; }
static_assert(OFF_U == 10 * 16384 && OFF_H == 12 * 16384 && OFF_OP == 2 * 16384 && OFF_Q + 6 * 4096 == 11 * 8192, "units");
__device__ __forceinline__ int g2_k(int hp, int i) {
  return i < 2 ? hp ^ 1 ^ i : i < 4 ? (hp & ~1) ^ i : ((hp & ~3) + i) & 15; }
__device__ __forceinline__ int y_slot(int wg, int it) {
  static_assert(T_B2 == T_TW + 8192 && T_A1 == T_B2 + 4096, "y slots");
  return OFF_T + T_TW + ((it + 3) & 3) * 4096 + wg * 2048;
}

__device__ __forceinline__ void to_arr(uint32_t (&d)[4], uint4 v) { d[0] = v.x; d[1] = v.y; d[2] = v.z; d[3] = v.w; }

__device__ __forceinline__ void attn_stage(uint32_t sb, int blk, int lane, const float (&acc)[96], uint32_t (&k1)[2][4]) {
  const int lr = lane & 7, lm = lane >> 3;
  const uint32_t base = sb + OFF_VP + (blk * 16 + lr + 8 * (lm & 1)) * 128;
#pragma unroll
  for (int i = 0; i < 8; i++) k1[i >> 2][i & 3] = pack_bf16(acc[34 + 4 * i], acc[35 + 4 * i]);
  const uint32_t kh = sb + OFF_OP + ((blk + 1) & 15) * 2048 + lane * 16;
  sts128(kh, k1[0][0], k1[0][1], k1[0][2], k1[0][3]);
  sts128(kh + 512, k1[1][0], k1[1][1], k1[1][2], k1[1][3]);
#pragma unroll
  for (int j = 0; j < 8; j += 2)
    stsm4(base + (((j + (lm >> 1)) ^ lr) << 4), pack_bf16(acc[64 + 4 * j], acc[65 + 4 * j]),
          pack_bf16(acc[66 + 4 * j], acc[67 + 4 * j]), pack_bf16(acc[68 + 4 * j], acc[69 + 4 * j]),
          pack_bf16(acc[70 + 4 * j], acc[71 + 4 * j]));
}
__device__ __forceinline__ void attn_pack(const float (&acc)[96], uint32_t (&qa)[2][8], uint32_t (&k0)[2][4]) {
#pragma unroll
  for (int hd = 0; hd < 2; hd++) {
#pragma unroll
    for (int i = 0; i < 8; i++) {
      asm volatile("cvt.rn.bf16x2.f32 %0, %1, %2;\n" : "=r"(qa[hd][i]) : "f"(acc[16 * hd + 2 * i + 1]), "f"(acc[16 * hd + 2 * i]));
    }
#pragma unroll
    for (int i = 0; i < 4; i++) {
      asm volatile("cvt.rn.bf16x2.f32 %0, %1, %2;\n" : "=r"(k0[hd][i]) : "f"(acc[33 + 16 * hd + 4 * i]), "f"(acc[32 + 16 * hd + 4 * i]));
    }
  }
}
__device__ __forceinline__ void attn_own(const uint32_t (&k0)[2][4], const uint32_t (&k1)[2][4], bool le0, bool le1,
                                         const uint32_t (&qa)[2][8], float (&l)[2][4]) {
#pragma unroll
  for (int hd = 0; hd < 2; hd++) {
    float s0[4], s1[4];
    mma16816_z(s0, qa[hd][0], qa[hd][1], qa[hd][2], qa[hd][3], k0[hd][0], k0[hd][1]);
    mma16816_z(s1, qa[hd][0], qa[hd][1], qa[hd][2], qa[hd][3], k1[hd][0], k1[hd][1]);
    mma16816(s0, qa[hd][4], qa[hd][5], qa[hd][6], qa[hd][7], k0[hd][2], k0[hd][3]);
    mma16816(s1, qa[hd][4], qa[hd][5], qa[hd][6], qa[hd][7], k1[hd][2], k1[hd][3]);
    l[hd][0] = s0[0];
    l[hd][1] = s0[1];
    l[hd][2] = le0 ? s1[2] : s0[2];
    l[hd][3] = le1 ? s1[3] : s0[3];
  }
}
template <int N> __device__ __forceinline__ void quad_softmax(float (&x)[N][2], uint32_t (&pp)[N]) {
  const float c2 = 1.4426950408889634f;
  uint32_t q[N], mx[N / 2];
#pragma unroll
  for (int n = 0; n < N; n++) {
    const uint32_t r = pack_bf16(x[n][0], x[n][1]);
    q[n] = bfma2(r, 0x3e353e35u, bmul2(r, 0x379e379eu));
    x[n][0] = bf_lo(q[n]);
    x[n][1] = bf_hi(q[n]);
  }
#pragma unroll
  for (int n = 0; n < N / 2; n++)
    mx[n] = bmax2(__byte_perm(q[2 * n], q[2 * n + 1], 0x5410), __byte_perm(q[2 * n], q[2 * n + 1], 0x7632));
#pragma unroll
  for (int o = 1; o <= 2; o++)
#pragma unroll
    for (int n = 0; n < N / 2; n++) mx[n] = bmax2(mx[n], __shfl_xor_sync(0xffffffffu, mx[n], o));
  float m[N], t[N];
#pragma unroll
  for (int n = 0; n < N / 2; n++) {
    m[2 * n] = bf_lo(mx[n]);
    m[2 * n + 1] = bf_hi(mx[n]);
  }
#pragma unroll
  for (int n = 0; n < N; n++) {
    const float nm = -m[n] * c2;
    x[n][0] = ex2(fmaf(x[n][0], c2, nm));
    x[n][1] = ex2(fmaf(x[n][1], c2, nm));
    t[n] = x[n][0] + x[n][1];
  }
#pragma unroll
  for (int o = 1; o <= 2; o++)
#pragma unroll
    for (int n = 0; n < N; n++) t[n] += __shfl_xor_sync(0xffffffffu, t[n], o);
#pragma unroll
  for (int n = 0; n < N; n++) {
    const float inv = rcp(t[n]);
    pp[n] = pack_bf16(x[n][0] * inv, x[n][1] * inv);
  }
}
__device__ __forceinline__ void attn_pv(uint32_t dst, const uint32_t (&va)[4], const uint32_t (&vb)[4], uint32_t pp,
                                        uint32_t maskLE) {
  const uint32_t b0 = pp & ~maskLE, b1 = pp & maskLE;
  float oa[4], ob[4];
  mma16816_z(oa, va[0], va[1], va[2], va[3], b0, b1);
  mma16816_z(ob, vb[0], vb[1], vb[2], vb[3], b0, b1);
  stsm4t(dst, pack_bf16(oa[0], oa[1]), pack_bf16(oa[2], oa[3]), pack_bf16(ob[0], ob[1]), pack_bf16(ob[2], ob[3]));
}

template <int MODE>
__global__ void __cluster_dims__(2, 1, 1) __launch_bounds__(NTHREADS, 1)
fused_kernel(const Params p, const __grid_constant__ CUtensorMap tmX, const __grid_constant__ CUtensorMap tmW,
             const __grid_constant__ CUtensorMap tmWo,
             const __grid_constant__ CUtensorMap tmQ,
             const __grid_constant__ CUtensorMap tmXh, const __grid_constant__ CUtensorMap tmWh) {
  extern __shared__ __align__(1024) uint8_t smem[];
  if (MODE != 2 && threadIdx.x < 28) {
    const uint32_t b = blockIdx.x & 127, t = threadIdx.x;
    prefetch_l2(t < 16 ? p.x + (b * 16 + t) * DM : p.w + (b * 12 + t - 16) * 64);
  }
  const uint32_t sb = smem_u32(smem) + HALO;
  const uint32_t bars = sb + OFF_BAR;
  const int tid = threadIdx.x, lane = tid & 31, warp = __shfl_sync(0xffffffffu, tid >> 5, 0);
  const int rank = blockIdx.x & 1;
  const bool halo_cta = blockIdx.x < 4;
  if (halo_cta && MODE != 0) return;
  int grp, mem;
  {
    const int t = (blockIdx.x >> 1) - 4, u = t - 32;
    const int q7 = (u * 37) >> 8;
    const bool lo = (unsigned)t < 32u, mid = (unsigned)u < 28u;
    grp = lo ? (t & 7) : (mid ? 1 + u - 7 * q7 : 0);
    mem = lo ? (t >> 3) : (mid ? 4 + q7 : (t < 0 ? t + 6 : t - 54));
  }
  const int rg = (grp >> 2) * 4 + (mem >> 1), hp = (grp & 3) * 4 + (mem & 1) * 2 + rank;
  const int rb2 = (grp >> 2) * 8 + mem, cb2 = (grp & 3) * 2 + rank;
  const int chb = grp * 16 + mem * 2 + rank;
  const int cta = rg * 16 + hp;
  const int par = rg >> 2, gidx = rg & 3;

  if (tid < 256 && !halo_cta && MODE != 2) {
    const int r = tid >> 3, c = tid & 7;
    const uint32_t so = r * 128 + ((c ^ (r & 7)) << 4);
    const __nv_bfloat16* wg0 = p.w + (size_t)r * (3 * DM) + hp * 64 + c * 8;
    const __nv_bfloat16* xg0 = p.x + (size_t)(2 * (gidx * 256 + r) + par) * DM + c * 8;
#pragma unroll
    for (int j = 0; j < 3; j++) cp_async16n(sb + OFF_1B + j * 4096 + so, wg0 + j * DM);
#pragma unroll
    for (int i = 0; i < 8; i++) cp_async16n(sb + i * 4096 + so, xg0 + (size_t)i * 64 * DM);
    asm volatile("cp.async.commit_group;\n" ::: "memory");
  }
  if (tid >= 368 && !halo_cta && MODE != 2)
    prefetch_l2(p.x + (size_t)(2 * (gidx * 256 + hp * 16 + (tid & 15)) + par) * DM + 64);
  if (tid == 256) {
    prefetch_tmap(halo_cta ? &tmXh : &tmX);
#pragma unroll
    for (int i = 0; i < NS1B; i++) mbar_init(bars + 8 * (BAR_FULLB + i), 1);
#pragma unroll
    for (int i = 0; i < NS1A; i++) mbar_init(bars + 8 * (BAR_FULLA + i), 1);
    asm volatile("fence.mbarrier_init.release.cluster;\n" ::: "memory");
    if (!halo_cta && MODE != 2) {
      mbar_expect_tx(bars + 8 * (BAR_FULLB + 1), STG1B);
      tma_load_3d(sb + OFF_1B + 1 * STG1B, &tmW, bars + 8 * (BAR_FULLB + 1), hp * 64, 32, 0);
      mbar_expect_tx(bars + 8 * (BAR_FULLB + 2), STG1B);
      tma_load_3d(sb + OFF_1B + 2 * STG1B, &tmW, bars + 8 * (BAR_FULLB + 2), hp * 64, 64, 0);
    } else {
      prefetch_tmap(&tmWh);
    }
  } else if (tid == 288) {
#pragma unroll
    for (int i = 0; i < NS1A; i++) mbar_init(bars + 8 * (BAR_EMPTYA + i), 4);
#pragma unroll
    for (int i = 0; i < NS1B; i++) mbar_init(bars + 8 * (BAR_EMPTYB + i), 2);
    asm volatile("fence.mbarrier_init.release.cluster;\n" ::: "memory");
  } else if (tid == 320) {
#pragma unroll
    for (int i = 0; i < NS2; i++) {
      mbar_init(bars + 8 * (BAR_FULL2 + i), 1);
      mbar_init(bars + 8 * (BAR_EMPTY2 + i), 4);
    }
    mbar_init(bars + 8 * BAR_DEAD, 2);
    mbar_init(bars + 8 * (BAR_DEAD + 1), 2);
    mbar_init(bars + 8 * BAR_X, 2);
    mbar_init(bars + 8 * BAR_REL, 2);
    asm volatile("fence.mbarrier_init.release.cluster;\n" ::: "memory");
  } else if (tid == 352) {
    mbar_init(bars + 8 * BAR_T, 1);
    mbar_init(bars + 8 * BAR_UH, 3);
    mbar_init(bars + 8 * BAR_LFREE, 4);
    mbar_init(bars + 8 * BAR_LAND, 1);
    mbar_init(bars + 8 * BAR_U, 1);
    mbar_init(bars + 8 * BAR_Q, 1);
    mbar_init(bars + 8 * BAR_STG, 9);
    asm volatile("fence.mbarrier_init.release.cluster;\n" ::: "memory");
  }
  if (warp == 8) PROF2(23);
  cluster_sync_all();
  if (warp == 8) PROF2(24);

  if (warp >= 8) {
    const int hw = warp - 8;
    const int lr = lane & 7, lm = lane >> 3;
    auto g1_issue_a = [&](int j, int s) {
      const uint32_t fb = bars + 8 * (BAR_FULLA + s);
      mbar_expect_tx(fb, STG1A);
      tma_load_3d_mc(sb + s * STG1A + rank * 16384, &tmX, fb, j * 64, par, gidx * 256 + rank * 128);
    };
    auto g1_issue_b = [&](int kb, int s) {
      const uint32_t fb = bars + 8 * (BAR_FULLB + s);
      mbar_expect_tx(fb, STG1B);
      tma_load_3d(sb + OFF_1B + s * STG1B, &tmW, fb, hp * 64, kb * 32, 0);
    };
    asm volatile("setmaxnreg.dec.sync.aligned.u32 %0;\n" :: "n"(REG_HELP));

    if (halo_cta) {
      if (hw == 0) {
        int s = 0, ph = 1;
#pragma unroll 1
        for (int kb = 0; kb < 16; kb++) {
          mbar_wait(bars + 8 * (BAR_EMPTYB + s), ph);
          const uint32_t fb = bars + 8 * (BAR_FULLB + s), st = sb + s * STGH;
          if (elect_one()) {
            mbar_expect_tx(fb, STGH);
            tma_load_4d(st, &tmXh, fb, kb * 64, 248, 0, 0);
            tma_load_3d(st + 8192, &tmWh, fb, 0, kb * 64, 16 + blockIdx.x * 4);
            tma_load_3d(st + 8192 + 32768, &tmWh, fb, 0, kb * 64, 32 + blockIdx.x * 4);
          }
          if (++s == 3) { s = 0; ph ^= 1; }
        }
      }
      __syncwarp();
    } else if (hw == 0) {
      uint32_t epoch = 0;
      if (lane < (MODE == 2 ? NS2 : 2)) mbar_arrive_cluster_n(mapa(bars, rank) + 8 * (BAR_EMPTY2 + lane), 4);
      if (MODE != 2) {
      epoch = ld_relaxed(g_flag_o + 2 * cta) + 1;
      if (lane == 0) {
        mbar_expect_tx(bars + 8 * BAR_U, 32768);
        mbar_expect_tx(bars + 8 * BAR_LAND, 32768 + 64);
        mbar_expect_tx(bars + 8 * BAR_Q, 32768);
        mbar_expect_tx(bars + 8 * BAR_T, T_END);
      }
      {
        int sa = 1, pha = 1, sbb = 2, phb = 1;
#pragma unroll 1
        for (int kb = 2; kb < 32; kb++) {
          if (!(kb & 1)) {
            mbar_wait(bars + 8 * (BAR_EMPTYA + sa), pha);
            if (elect_one()) g1_issue_a(kb >> 1, sa);
            if (++sa == NS1A) { sa = 0; pha ^= 1; }
          }
          mbar_wait(bars + 8 * (BAR_EMPTYB + sbb), phb);
          if (kb > 2 && elect_one()) g1_issue_b(kb, sbb);
          __syncwarp();
          if (kb >= PF0 && kb < PF0 + 12)
            prefetch_l2((kb < PF0 + 8 ? p.q + (size_t)chb * 16384 + (kb - PF0) * 2048 : p.wo + (size_t)chb * 8192 + (kb - PF0 - 8) * 2048) + lane * 64);
          if (kb == 4) PROF2(27);
          if (kb == 1) PROF2(38);
          if (kb == 2) PROF2(39);
          if (++sbb == NS1B) { sbb = 0; phb ^= 1; }
        }
      }
      static_assert(32 % NS1B == 2 && (32 / NS1B) % 2 == 0 && OFF_Q + STG2 + 6 * 4096 == OFF_1B + 2 * STG1B, "slots / parity of these loads");
      const uint8_t* tab = reinterpret_cast<const uint8_t*>(g_tab);
      if (lane == 0) {
        prefetch_tmap(&tmWo);
        prefetch_tmap(&tmQ);
        bulk_load(sb + OFF_T + T_A1, tab + T_A1, T_END - T_A1, bars + 8 * BAR_T);
        mbar_wait(bars + 8 * (BAR_EMPTYB + 2), 1);
        tma_load_5d(sb + OFF_Q + STG2 + 6 * 4096, &tmQ, bars + 8 * BAR_Q, (chb & ~1) * 8, rank * 32 + 24);
        tma_load_5d(sb + OFF_Q + STG2 + 7 * 4096, &tmQ, bars + 8 * BAR_Q, (chb & ~1) * 8, rank * 32 + 28);
        if (gidx != 0) wait_flag(g_flag_h + (hp >> 2), epoch);
      }
      __syncwarp();
      {
        uint4 hk0 = make_uint4(0, 0, 0, 0), hk1 = hk0, hv0 = hk0, hv1 = hk0;
        if (gidx != 0) {
          const uint4* src = g_halo + cta * 128 + lane;
          hk0 = __ldcg(src); hk1 = __ldcg(src + 32); hv0 = __ldcg(src + 64); hv1 = __ldcg(src + 96);
        }
        if (lane == 0) {
          mbar_wait(bars + 8 * (BAR_EMPTYB + 3), 1);
          bulk_load(sb + OFF_T, tab, T_TW, bars + 8 * BAR_T);
        }
        __syncwarp();
        PROF2(18);
        sts128(sb - HALO + lane * 16, hk0.x, hk0.y, hk0.z, hk0.w);
        sts128(sb - HALO + 512 + lane * 16, hk1.x, hk1.y, hk1.z, hk1.w);
        stsm4(sb - HALO + 1024 + lr * 128 + ((lm ^ lr) << 4), hv0.x, hv0.y, hv0.z, hv0.w);
        stsm4(sb - HALO + 1024 + lr * 128 + (((4 + lm) ^ lr) << 4), hv1.x, hv1.y, hv1.z, hv1.w);
        __syncwarp();
        if (lane == 0) {
          mbar_arrive(bars + 8 * BAR_STG);
          mbar_wait(bars + 8 * (BAR_EMPTYB + 4), 1);
          bulk_load(sb + OFF_T + T_TW, tab + T_TW, T_A1 - T_TW, bars + 8 * BAR_T);
#pragma unroll 1
          for (int i = 0; i < 6; i++) tma_load_5d(sb + OFF_Q + i * 4096, &tmQ, bars + 8 * BAR_Q, (chb & ~1) * 8, rank * 32 + i * 4);
          if (MODE == 0) {
            mbar_wait(bars + 8 * BAR_EMPTYB, 0);
            tma_load_3d(sb + g2_b(0), &tmWo, bars + 8 * BAR_FULL2, 0, g2_k(hp, 0) * 64, cb2 * 2);
            tma_load_3d(sb + g2_b(1), &tmWo, bars + 8 * (BAR_FULL2 + 1), 0, g2_k(hp, 1) * 64, cb2 * 2);
          }
        }
        __syncwarp();
      }
      }
      if (MODE != 1) {
        auto korder = [&](int i) { return MODE == 2 ? i : g2_k(hp, i); };
        const __nv_bfloat16* osrc = g_o + (size_t)(rb2 >> 1) * 16 * 16384 + ((rb2 & 1) * 2 + rank) * 4096;
        const uint32_t* flag = g_flag_o + ((rb2 >> 1) * 32 + korder(lane & 15) * 2 + (rb2 & 1));
        uint32_t ready = MODE == 0 ? 0u : ~0u, pv = 0;
        const __nv_bfloat16* o23[2] = {osrc + korder(2) * 16384, osrc + korder(3) * 16384};
        if (MODE == 0) {
          asm volatile("" : "+l"(o23[0]), "+l"(o23[1]), "+l"(flag));
          if (lane < 4 && lane != 1) mbar_expect_tx(bars + 8 * (BAR_FULL2 + lane), STG2);
          mbar_wait_idle(bars + 8 * (BAR_EMPTY2 + 2), 0);
          mbar_wait(bars + 8 * (BAR_EMPTY2 + 3), 0);
          mbar_wait_idle(bars + 8 * BAR_REL, 0);
          const uint32_t t0 = clock();
          while ((uint32_t)clock() - t0 < 500u) __nanosleep(20);
        }
#pragma unroll
        for (int i = MODE == 0 ? 2 : 0; i < 16; i++) {
          const int kb = korder(i), s = i % NS2, ph = (i / NS2) & 1;
          const uint32_t fb = bars + 8 * (BAR_FULL2 + s);
          if (!((ready >> i) & 1)) {
            int n = 0;
            do {
              ready |= __ballot_sync(0xffffffffu, ld_acquire(flag) == epoch);
            } while (!((ready >> i) & 1) && ++n < SPIN_LIMIT);
            fence_async_all();
          }
          if (i == 2) PROF(21);
          const bool pre = MODE == 0 && i < 4;
          if (!pre) mbar_wait(bars + 8 * (BAR_EMPTY2 + s), ph);
          if (elect_one()) {
            if (!pre) mbar_expect_tx(fb, STG2);
            asm volatile(
                "cp.async.bulk.shared::cluster.global.mbarrier::complete_tx::bytes.multicast::cluster [%0], [%1], %2, [%3], %4;\n"
                ::"r"(sb + g2_a(s, rb2 & 1) + rank * 8192), "l"(pre ? o23[i & 1] : osrc + kb * 16384), "r"(8192), "r"(fb), "h"((uint16_t)3) : "memory");
            if (!pre) tma_load_3d(sb + g2_b(s), &tmWo, fb, 0, kb * 64, cb2 * 2);
          }
          if (i == 3 && ready != ~0u) pv = ld_relaxed(flag);
          if (i == 4 && ready != ~0u) {
            ready |= __ballot_sync(0xffffffffu, pv == epoch);
            asm volatile("fence.acquire.gpu;\n" ::: "memory");
            fence_async_all();
          }
          if (i == 3) PROF(37);

        }
      }
      __syncwarp();
    } else if (MODE != 2) {
      {
        const int g = lane >> 2, t = lane & 3;
        uint32_t w[2][4];
#pragma unroll
        for (int h = 0; h < 2; h++) {
          const uint2 x = __ldg(reinterpret_cast<const uint2*>(p.shift_k + ((chb & ~1) * 8 + h * 8 + g) * 4));
          w[h][0] = __byte_perm(x.x, x.x, 0x1010);
          w[h][1] = __byte_perm(x.x, x.x, 0x3232);
          w[h][2] = __byte_perm(x.y, x.y, 0x1010);
          w[h][3] = __byte_perm(x.y, x.y, 0x3232);
        }
        auto swz = [](int r) { return (((r & 29) | ((r ^ (r >> 2)) & 2)) << 5) | (r & 16); };
        const uint32_t kring = sb + OFF_H + (hw - 1) * 8192, vring = kring + 4096;
        const int s0 = rank * 32 + (hw - 1) * 11, s1 = hw == 3 ? rank * 32 + 32 : s0 + 11;
        const size_t goff = (size_t)(lane >> 1) * DM + (chb & ~1) * 8 + (lane & 1) * 8;
        const __nv_bfloat16* kg = p.k + goff;
        const __nv_bfloat16* vg = p.v + goff;
        const uint32_t d0 = swz(lane >> 1) ^ ((lane & 1) << 4), d1 = swz(16 + (lane >> 1)) ^ ((lane & 1) << 4);
        auto issue = [&](int st) {
          const uint32_t so = (st & 3) << 10;
          cp_async16(kring + so + d0, kg + (size_t)st * 32 * DM, 16);
          cp_async16(kring + so + d1, kg + (size_t)(st * 32 + 16) * DM, 16);
          cp_async16(vring + so + d0, vg + (size_t)st * 32 * DM, 16);
          cp_async16(vring + so + d1, vg + (size_t)(st * 32 + 16) * DM, 16);
        };
        const int xa = 8 * (lr >> 1) + 2 * lm + (lr & 1), xb = 8 * (lr >> 1) - 4 + 2 * (lm & 1) + (lr & 1);
        const uint32_t la = swz(xa), lb = swz(xb & 31);
        const int backb = xb < 0 ? 1 : 0;
        const uint32_t ud[2] = {mapa(sb + OFF_U + g * 4096 + t * 16, 0), mapa(sb + OFF_U + g * 4096 + t * 16, 1)};
        const uint32_t ub[2] = {mapa(bars + 8 * BAR_U, 0), mapa(bars + 8 * BAR_U, 1)};
        if (lane == 0) mbar_wait(bars + 8 * (BAR_FULLB + NS1B - 1), 0);
        __syncwarp();
        if (lane >= 24) cp_async16(kring + (((s0 - 1) & 3) << 10) + d1, s0 > 0 ? kg + (size_t)(s0 * 32 - 16) * DM : kg, s0 > 0 ? 16 : 0);
        issue(s0);
        asm volatile("cp.async.commit_group;\n" ::: "memory");
        issue(s0 + 1);
        asm volatile("cp.async.commit_group;\n" ::: "memory");
#pragma unroll 1
        for (int st = s0; st < s1; st++) {
          if (st + 2 < s1) issue(st + 2);
          if (hw == 1 && st - s0 < 8) prefetch_l2(p.ssm_k + (size_t)(chb * 8 + st - s0) * SEQ + lane * 64);
          if (hw == 2 && st == s0 + 4 && lane < 2) prefetch_l2(g_tab + (chb * 2 + lane) * 32);
          const uint32_t uo = (st ^ ((g ^ (st >> 2)) & 1)) * 64;
          asm volatile("cp.async.commit_group;\n" ::: "memory");
          asm volatile("cp.async.wait_group 2;\n" ::: "memory");
          __syncwarp();
#pragma unroll
          for (int h = 0; h < 2; h++) {
            uint32_t e[6], vv[4], e4[4];
            ldsm4t(e4, kring + ((st & 3) << 10) + (la ^ (h << 4)));
            ldsm2t(e[0], e[1], kring + (((st - backb) & 3) << 10) + (lb ^ (h << 4)));
            ldsm4t(vv, vring + ((st & 3) << 10) + (la ^ (h << 4)));
            e[2] = e4[0]; e[3] = e4[1]; e[4] = e4[2]; e[5] = e4[3];
            uint32_t o[5];
#pragma unroll
            for (int i = 0; i < 5; i++) o[i] = __byte_perm(e[i], e[i + 1], 0x5432);
#pragma unroll
            for (int i = 0; i < 4; i++) {
              uint32_t a = bmul2(o[i], w[h][3]);
              a = bfma2(e[i + 1], w[h][2], a);
              a = bfma2(o[i + 1], w[h][1], a);
              a = bfma2(e[i + 2], w[h][0], a);
              vv[i] = bmul2(a, vv[i]);
            }
            st_async128(ud[h] + uo, ub[h], vv[0], vv[1], vv[2], vv[3]);
          }
          __syncwarp();
        }
        PROF(16);
      }
      {
        const int rw = (lane >> 3) + (lane & 4), ck = lane & 3;
        const uint32_t so = rw * 64 + ck * 16, dof = rw * 128 + ((ck ^ rw) << 4);
        const uint8_t* hsrc = reinterpret_cast<const uint8_t*>(p.ssm_k + (size_t)chb * 8 * SEQ) + so;
        const float dv = lane < 8 ? __bfloat162float(p.ssm_D[chb * 8 + lane]) : 0.f;
        uint32_t x[32];
        auto load = [&](const uint8_t* src, int i) {
          asm volatile("ld.v4.u32 {%0,%1,%2,%3}, [%4];\n" : "=r"(x[4 * i]), "=r"(x[4 * i + 1]), "=r"(x[4 * i + 2]), "=r"(x[4 * i + 3])
                       : "l"(src + i * 512) : "memory");
        };
#pragma unroll
        for (int i = 0; i < 8; i++) load(hsrc + (hw - 1) * 4096, i);
        nb_sync(NB_HELP3, 96);
        mbar_wait(bars + 8 * BAR_U, 0);
        int eh = 0;
#pragma unroll 1
        for (int n = 2 * (hw - 1); n < 16; n += (n & 1) ? 5 : 1) {
          const int c = n >> 1;
          const uint8_t* nsrc = (n & 1) ? hsrc + (c < 5 ? c + 3 : c) * 4096
                                        : smem + HALO + OFF_U + c * 4096 + (so ^ (((c ^ (lane >> 2)) & 1) << 6));
          const uint32_t dst = sb + ((n & 1) ? OFF_U : OFF_H) + c * 4096 + dof;
          const float dc = __shfl_sync(0xffffffffu, dv, c);
          const float h0 = bf_lo(x[0]) + ((lane | (n & 1)) == 0 ? dc : 0.f), h1 = bf_hi(x[0]);
          x[0] = pack_bf16(h0, h1);
          uint32_t m[2] = {x[0], x[1]};
#pragma unroll
          for (int i = 2; i < 32; i++) asm("max.xorsign.abs.bf16x2 %0, %0, %1;\n" : "+r"(m[i & 1]) : "r"(x[i]));
          asm("max.xorsign.abs.bf16x2 %0, %0, %1;\n" : "+r"(m[0]) : "r"(m[1]));
          const uint32_t e = max(__reduce_max_sync(0xffffffffu, max((m[0] >> 7) & 255u, (m[0] >> 23) & 255u)), 5u);
          const uint32_t sc = (259u - e) * 0x00800080u;
#pragma unroll
          for (int i = 0; i < 8; i++) {
            uint32_t o[4];
#pragma unroll
            for (int j = 0; j < 4; j++) {
              const uint32_t v = bmul2(x[4 * i + j], sc);
              asm("cvt.rn.f16x2.f32 %0, %1, %2;\n" : "=r"(o[j]) : "f"(bf_hi(v)), "f"(i + j == 0 ? h0 * bf_hi(sc) : bf_lo(v)));
            }
            sts128((dst + (i & 3) * 1024) ^ ((i >> 2) << 6), o[0], o[1], o[2], o[3]);
            load(nsrc, i);
          }
          if (n & 1) {
            const int f = min(max((int)e + eh - 129, 0), 254);
            if (lane < 2)
              asm volatile("st.async.weak.shared::cluster.mbarrier::complete_tx::bytes.b32 [%0], %2, [%1];\n"
                           ::"r"(mapa(sb + OFF_SC + rank * 32 + c * 4, lane)), "r"(mapa(bars + 8 * BAR_LAND, lane)), "r"(f << 7) : "memory");
          }
          eh = e;
        }
        fence_async_smem();
        __syncwarp();
        if (lane == 0) mbar_arrive(bars + 8 * BAR_UH);
        PROF(32);
      }
      if (hw < 3) {
        const uint32_t rb = mapa(bars, lane & 1);
        const uint32_t epoch = ld_relaxed(g_flag_o + (2 * cta + hw - 1)) + 1;
        const bool own = hw - 1 == (rb2 & 1);
        nb_sync(NB_OREADY + hw - 1, 160);
        if (lane == 0) {
          asm volatile("cp.async.bulk.global.shared::cta.bulk_group [%0], [%1], %2;\n" ::"l"(g_o + (size_t)cta * 16384 + (hw - 1) * 8192),
                       "r"(sb + OFF_OP + (hw - 1) * 16384), "r"(16384) : "memory");
          bulk_commit();
        }
        if (lane < 2) {
          mbar_arrive_cluster(rb + 8 * (BAR_EMPTY2 + 2));
          mbar_arrive_cluster(rb + 8 * (BAR_EMPTY2 + 3));
        }
        if (lane == 0) {
          bulk_wait0();
          if (own) mbar_expect_tx(bars + 8 * (BAR_FULL2 + 1), 16384);
          mbar_arrive_cluster(mapa(bars, own ? rank : rank ^ 1) + 8 * BAR_X);
          st_release(g_flag_o + (2 * cta + hw - 1), epoch);
          mbar_arrive(bars + 8 * BAR_REL);
        }
        __syncwarp();
        PROF(own ? 17 : 19);
      } else {
        if (MODE == 0) {
          mbar_wait_idle(bars + 8 * BAR_X, 0);
          if (elect_one())
            asm volatile("cp.async.bulk.shared::cluster.shared::cta.mbarrier::complete_tx::bytes [%0], [%1], %2, [%3];\n"
                         ::"r"(mapa(sb + g2_a(0, rb2 & 1), rank ^ 1)), "r"(sb + g2_a(1, rb2 & 1)), "r"(16384),
                         "r"(mapa(bars + 8 * BAR_FULL2, rank ^ 1)) : "memory");
        }
        if (MODE == 0) {
          mbar_wait_idle(bars + 8 * BAR_DEAD, 0);
          if (elect_one()) {
            tma_load_3d(sb + g2_b(2), &tmWo, bars + 8 * (BAR_FULL2 + 2), 0, g2_k(hp, 2) * 64, cb2 * 2);
            tma_load_3d(sb + g2_b(3), &tmWo, bars + 8 * (BAR_FULL2 + 3), 0, g2_k(hp, 3) * 64, cb2 * 2);
          }
        }
        __syncwarp();
      }
    }
    if (!halo_cta && MODE != 2) {
      {
        const int c8 = (4 * (lr >> 1) + 2 * (lm & 1) + (lr & 1)) & 7;
        const bool own = (lr >> 2) == rank;
        const uint32_t ya = sb + (own ? y_slot(c8 & 1, c8 >> 1) : OFF_LAND + c8 * 2048);
        const uint32_t yx = ((lm >> 1) ^ lr) << 4;
        const int row = (lane >> 4) * 8 + ((lane >> 3) & 1) * 16 + ((lane >> 2) & 1);
        uint2* og = reinterpret_cast<uint2*>(p.out + (size_t)(rank * 1024 + row) * (2 * DM) + (chb & ~1) * 8 + (lane & 3) * 4);
        const uint32_t qa = sb + OFF_Q + (lane >> 4) * 512 + (lane & 15) * 8;
        mbar_wait(bars + 8 * BAR_Q, 0);
        mbar_wait_idle(bars + 8 * BAR_LAND, 0);
        PROF(33);
        const uint32_t t0 = clock();
        const uint4 s4 = lds128(sb + OFF_SC + (lane & 3) * 16);
        const uint32_t sc[2] = {s4.x | (s4.y << 16), s4.z | (s4.w << 16)};
        auto fin = [&](uint32_t q2, uint32_t y2, uint32_t s2) {
          float lo, hi;
          asm("{\n.reg .b16 l, h;\nmov.b32 {l, h}, %2;\ncvt.f32.f16 %0, l;\ncvt.f32.f16 %1, h;\n}\n" : "=f"(lo), "=f"(hi) : "r"(y2));
          return bmul2(q2, bmul2(pack_bf16(lo, hi), s2));
        };
#pragma unroll 1
        for (int j = hw ? hw - 1 : 15; j < (hw ? 15 : 16); j += 3) {
          uint32_t y[4][4];
          uint2 q[8];
          while (hw && (uint32_t)clock() - t0 < j * PACE) __nanosleep(40);
          const uint32_t qj = qa + j * 2048 + (j >= 12 ? STG2 : 0);
#pragma unroll
          for (int i = 0; i < 4; i++) ldsm4t(y[i], ya + j * 128 + (yx ^ (i << 5)));
#pragma unroll
          for (int i = 0; i < 8; i++) q[i] = lds64(qj + (i >> 2) * 1024 + (i & 3) * 128);
#pragma unroll
          for (int i = 0; i < 8; i++) {
            og[(size_t)(j * 64 + (i >> 2) * 32 + (i & 3) * 2) * (2 * DM / 4)] =
                make_uint2(fin(q[i].x, y[i >> 1][2 * (i & 1)], sc[0]), fin(q[i].y, y[i >> 1][2 * (i & 1) + 1], sc[1]));
            if (i < 7) asm volatile("nanosleep.u32 40;\n" ::: "memory");
          }
        }
      }
      PROF(22);
    }
    cluster_sync_all();
  } else {
    asm volatile("setmaxnreg.inc.sync.aligned.u32 %0;\n" :: "n"(REG_MATH));
    if (warp == 0) PROF2(26);
    const int wg = warp >> 2;
    const int wtid = tid & 127;
    const bool signaller = (wtid == 0) || (wtid == 32);
    const uint32_t rbars = mapa(bars, wtid >> 5 & 1);

    if (halo_cta) {
      const uint32_t epoch = ld_relaxed(g_flag_h + blockIdx.x) + 1;
      float acc0[64], acc1[64];
      int s = 0, ph = 0;
#pragma unroll 1
      for (int kb = 0; kb < 16; kb++) {
        mbar_wait(bars + 8 * (BAR_FULLB + s), ph);
        const uint32_t st = sb + s * STGH;
        const uint64_t da = mkdesc(st, 16, 1024, 1);
        const uint64_t db = mkdesc(st + 8192 + wg * 32768, 8192, 1024, 1);
        wg_fence();
#pragma unroll
        for (int kk = 0; kk < 4; kk++) {
          wgmma_n128(acc0, da + 2 * kk, db + 128 * kk, kb + kk);
          wgmma_n128(acc1, da + 2 * kk, db + 1024 + 128 * kk, kb + kk);
        }
        wg_commit();
        wg_wait<0>();
        if (wtid == 0) mbar_arrive(bars + 8 * (BAR_EMPTYB + s));
        if (++s == 3) { s = 0; ph ^= 1; }
      }
      fence_regs(acc0);
      fence_regs(acc1);
      if ((warp & 3) != 3) {
#pragma unroll
        for (int hh = 0; hh < 2; hh++) {
          uint4* dst = g_halo + ((hh * 4 + (warp & 3) + 1) * 16 + blockIdx.x * 4) * 128 + wg * 64 + lane;
#pragma unroll
          for (int j = 0; j < 4; j++) {
            const int o = 16 * j + 2 * hh;
            dst[(j >> 1) * 128 + (j & 1) * 32] =
                make_uint4(pack_bf16(acc0[o], acc0[o + 1]), pack_bf16(acc0[o + 4], acc0[o + 5]),
                           pack_bf16(acc0[o + 8], acc0[o + 9]), pack_bf16(acc0[o + 12], acc0[o + 13]));
            dst[(2 + (j >> 1)) * 128 + (j & 1) * 32] =
                make_uint4(pack_bf16(acc1[o], acc1[o + 1]), pack_bf16(acc1[o + 4], acc1[o + 5]),
                           pack_bf16(acc1[o + 8], acc1[o + 9]), pack_bf16(acc1[o + 12], acc1[o + 13]));
          }
        }
      }
      nb_sync(NB_G1DONE, 256);
      if (tid == 0) st_release(g_flag_h + blockIdx.x, epoch);
      PROF(36);
      cluster_sync_all();
      return;
    }

    float acc[64];
    auto g2_step = [&](int s, int kb) {
      const uint64_t da = mkdesc(sb + g2_a(s, rb2 & 1) + wg * 8192, 16, 1024, 1);
      const uint64_t db = mkdesc(sb + g2_b(s), 8192, 1024, 1);
      wg_fence();
      wgmma_n128(acc, da, db, kb);
      wgmma_n128(acc, da + 2, db + 128, 1);
      wgmma_n128(acc, da + 4, db + 256, 1);
      wgmma_n128(acc, da + 6, db + 384, 1);
      wg_commit();
    };

    if (MODE != 2) {
    uint32_t a1[2][4], tw[12], d1[32];
    const uint32_t tb = sb + OFF_T + wtid * 16;
    const uint64_t dx = mkdesc(sb + OFF_U + wg * 4096, OFF_H - OFF_U, 1024, 1);
    auto s1 = [&](int it) {
      hmma_n128t<0>(d1, a1[0], dx + it * 512);
      hmma_n128t<1>(d1, a1[1], dx + it * 512 + 128);
      wg_commit();
    };
    auto ldtw = [&](int i) {
      const uint4 v = lds128(tb + T_TW + i * 2048);
      tw[4 * i] = v.x; tw[4 * i + 1] = v.y; tw[4 * i + 2] = v.z; tw[4 * i + 3] = v.w;
    };
    {
      float acc0[96], acc1[96];
      int sa = 0, pha = 0, sbb = 0, phb = 0;
      asm volatile("cp.async.wait_group 0;\n" ::: "memory");
      fence_async_smem();
      nb_sync(NB_FIRST, 256);
      if (tid == 0) {
        mbar_arrive(bars + 8 * BAR_FULLA);
        mbar_arrive(bars + 8 * BAR_FULLB);
      }
      PROF(0 + wg);
#pragma unroll 1
      for (int kb = 0; kb < 30; kb++) {
        if (!(kb & 1)) mbar_wait(bars + 8 * (BAR_FULLA + sa), pha);
        mbar_wait(bars + 8 * (BAR_FULLB + sbb), phb);
        if (kb == 0) PROF2(0 + wg);
        if (kb == 4 && wg == 0) PROF2(28);
        if (kb == 8 && wg == 0) PROF2(29);
        if (kb == 16 && wg == 0) PROF2(30);
        const uint64_t da = mkdesc(sb + sa * STG1A + wg * 16384 + (kb & 1) * 64, 16, 1024, 1);
        const uint64_t db = mkdesc(sb + OFF_1B + sbb * STG1B, 4096, 1024, 1);
        wg_fence();
        wgmma_n192(acc0, da, db, kb);
        wgmma_n192(acc1, da + 512, db, kb);
        wgmma_n192(acc0, da + 2, db + 128, 1);
        wgmma_n192(acc1, da + 514, db + 128, 1);
        wg_commit();
        wg_wait<1>();
        if (kb > 0) {
          if (wtid == 64) mbar_arrive(bars + 8 * (BAR_EMPTYB + (sbb == 0 ? NS1B - 1 : sbb - 1)));
          if (!(kb & 1) && signaller) mbar_arrive_cluster(rbars + 8 * (BAR_EMPTYA + (sa == 0 ? NS1A - 1 : sa - 1)));
        }
        if (++sbb == NS1B) { sbb = 0; phb ^= 1; }
        if ((kb & 1) && ++sa == NS1A) { sa = 0; pha ^= 1; }
      }
      const int blk0 = wg * 8 + (warp & 3);
      const int lr = lane & 7, lm = lane >> 3;
      const bool le0 = 2 * (lane & 3) <= (lane >> 2), le1 = 2 * (lane & 3) + 1 <= (lane >> 2);
      const uint32_t maskLE = (le0 ? 0x0000FFFFu : 0u) | (le1 ? 0xFFFF0000u : 0u);
      uint32_t k0[2][2][4], k1[2][2][4], qa[2][2][8];
      float l[2][2][4];
      {
        static_assert(15 % NS1A == 0 && 30 % NS1B == 0, "slots of the last k blocks");
        mbar_wait(bars + 8 * BAR_FULLA, 1);
        mbar_wait(bars + 8 * BAR_FULLB, 0);
        mbar_wait(bars + 8 * (BAR_FULLB + 1), 0);
        mbar_wait(bars + 8 * (BAR_EMPTYB + 2), 1);
        const uint64_t da = mkdesc(sb + wg * 16384, 16, 1024, 1);
        const uint64_t db = mkdesc(sb + OFF_1B, 4096, 1024, 1);
        wg_fence();
#pragma unroll
        for (int i = 0; i < 4; i++) wgmma_n192(acc0, da + 2 * i, db + (i >> 1) * (STG1B >> 4) + (i & 1) * 128, 1);
        wg_commit();
        wg_wait<1>();
        if (wtid == 64) mbar_arrive(bars + 8 * (BAR_EMPTYB + NS1B - 1));
#pragma unroll
        for (int i = 0; i < 2; i++) wgmma_n192(acc1, da + 512 + 2 * i, db + (i >> 1) * (STG1B >> 4) + (i & 1) * 128, 1);
        wg_commit();
        wg_wait<1>();
        fence_regs(acc0);
        attn_stage(sb, blk0, lane, acc0, k1[0]);
#pragma unroll
        for (int i = 2; i < 4; i++) wgmma_n192(acc1, da + 512 + 2 * i, db + (i >> 1) * (STG1B >> 4) + (i & 1) * 128, 1);
        wg_commit();
        attn_pack(acc0, qa[0], k0[0]);
        wg_wait<0>();
        fence_regs(acc1);
      }
      if (wtid == 64) mbar_arrive(bars + 8 * BAR_EMPTYB);
      PROF(2 + wg);
      attn_stage(sb, blk0 + 4, lane, acc1, k1[1]);
      __syncwarp();
      if (lane == 0) mbar_arrive(bars + 8 * BAR_STG);
      mbar_wait(bars + 8 * BAR_U, 0);
      attn_pack(acc1, qa[1], k0[1]);
      attn_own(k0[0], k1[0], le0, le1, qa[0], l[0]);
      attn_own(k0[1], k1[1], le0, le1, qa[1], l[1]);
      static_assert(OFF_VP == 0, "halo V rows");
      const uint32_t vl0 = sb + OFF_VP - 1024 + blk0 * 2048 + (lm >> 1) * 1024 + lr * 128 + (((lm & 1) ^ lr) << 4);
      const uint32_t vl[4] = {vl0, vl0 ^ 64, vl0 ^ 32, vl0 ^ 96};
      const uint32_t obase = sb + OFF_OP + (blk0 * 16 + lr) * 128 + ((lm ^ lr) << 4);
      mbar_wait(bars + 8 * BAR_STG, 0);
      {
        uint32_t km[4][4], va[8][4], vb[8][4], pp[8];
        float x[8][2];
#pragma unroll
        for (int n = 0; n < 4; n++) {
          const int blk = blk0 + 4 * (n >> 1);
          to_arr(km[n], lds128(sb + (blk == 0 ? -HALO : OFF_OP + blk * 2048) + (n & 1) * 512 + lane * 16));
        }
#pragma unroll
        for (int n = 0; n < 8; n++) {
          const uint32_t o = ((n >> 1) & 1) * 8192 + (n >> 2) * 1024;
          ldsm4t(va[n], vl[n & 1] + o);
          ldsm4t(vb[n], vl[2 + (n & 1)] + o);
        }
        const bool first = blk0 == 0 && gidx == 0;
#pragma unroll
        for (int n = 0; n < 4; n++) {
          const uint32_t(&q)[8] = qa[n >> 1][n & 1];
          float sm[4];
          mma16816_z(sm, q[0], q[1], q[2], q[3], km[n][0], km[n][1]);
          mma16816(sm, q[4], q[5], q[6], q[7], km[n][2], km[n][3]);
          if (n < 2 && first) sm[0] = sm[1] = -1e9f / 0.17677669529663687f;
          x[n][0] = le0 ? l[n >> 1][n & 1][0] : sm[0];
          x[n][1] = le1 ? l[n >> 1][n & 1][1] : sm[1];
          x[4 + n][0] = l[n >> 1][n & 1][2];
          x[4 + n][1] = l[n >> 1][n & 1][3];
        }
        quad_softmax<8>(x, pp);
#pragma unroll
        for (int n = 7; n >= 0; n--)
          attn_pv((obase ^ ((n & 1) << 6)) + ((n >> 1) & 1) * 8192 + (n >> 2) * 1024, va[n], vb[n], pp[n], maskLE);
      }
      fence_async_smem();
      nb_arrive(NB_OREADY + wg, 160);
    }

    {
      const int w = warp & 3;
      uint32_t a4[8][4];
      uint32_t d4[16];
      PROF(34 + wg);
      const uint64_t dz = mkdesc(sb + OFF_U + wg * 4096, 1024, 128, 0);
      const uint64_t db2 = mkdesc(sb + OFF_T + T_B2, 128, 512, 0), db3 = mkdesc(sb + OFF_T + T_B2, 1024, 128, 0);
      mbar_wait(bars + 8 * BAR_T, 0);
      mbar_wait(bars + 8 * BAR_UH, 0);
      to_arr(a1[0], lds128(tb + T_A1));
      to_arr(a1[1], lds128(tb + T_A1 + 2048));
      wg_fence();
      s1(0);
      ldtw(0);
      ldtw(1);
      const uint32_t za = sb + (w < 2 ? OFF_U : OFF_H) + wg * 4096 + (w & 1) * 8192 + lane * 16;
      const uint32_t yl = (wtid ^ (4 * rank + wg)) * 16;
      const uint32_t yown = mapa(sb, rank) + yl, yrem = mapa(sb + OFF_LAND + wg * 2048, rank ^ 1) + yl;
      const uint32_t yb[2] = {mapa(bars + 8 * BAR_LAND, 0), mapa(bars + 8 * BAR_LAND, 1)};
      wg_wait<0>();
      fence_regs(d1);
      auto s4 = [&]() {
        wg_fence();
#pragma unroll
        for (int ks = 0; ks < 8; ks++) {
          const uint64_t d = dz + (ks & 1) * 128 + ((ks >> 1) & 1) * 512 + (ks >> 2) * ((OFF_H - OFF_U) >> 4);
          if (ks == 0) hmma_n64t<0>(d4, a4[ks], d);
          else hmma_n64t<1>(d4, a4[ks], d);
        }
        wg_commit();
      };
      auto e4 = [&](int pr) {
        fence_regs(d4);
        mbar_wait(bars + 8 * (pr == 0 ? BAR_LFREE : BAR_DEAD + 1), 0);
#pragma unroll
        for (int u = 0; u < 2; u++) {
          const int it = 2 * pr + u;
          const uint32_t o = (yown + y_slot(wg, it)) ^ (pr << 5), m = (yrem + it * 4096) ^ (pr << 5);
          st_async128(rank ? m : o, yb[0], d4[8 * u], d4[8 * u + 1], d4[8 * u + 2], d4[8 * u + 3]);
          st_async128(rank ? o : m, yb[1], d4[8 * u + 4], d4[8 * u + 5], d4[8 * u + 6], d4[8 * u + 7]);
        }
      };
      uint32_t a2[2][2][2][4], a3[2][2][4], d2[2][2][8], d3[2][8];
      auto s2a = [&]() {
        wg_fence();
#pragma unroll
        for (int c = 0; c < 4; c++) hmma_n32<0, 0>(d2[c & 1][c >> 1], a2[0][c & 1][c >> 1], db2 + (c >> 1) * 128);
      };
      auto s2b = [&]() {
        wg_fence();
#pragma unroll
        for (int c = 0; c < 4; c++) {
          hmma_n32<1, 0>(d2[c & 1][c >> 1], a2[1][c & 1][c >> 1], db2 + (c >> 1) * 128 + 16);
          if (c & 1) wg_commit();
        }
      };
      fft_e1<0>(d1, tw, a2[0]);
      s2a();
      fft_e1<1>(d1, tw, a2[1]);
      s2b();
      s1(1);
      ldtw(2);
#pragma unroll
      for (int i = 0; i < 8; i++) to_arr(a4[i], lds128(tb + T_A4 + i * 2048));
#pragma unroll
      for (int it = 0; it < 4; it++) {
        if (it == 2) wg_wait<3>(); else if (it == 3) wg_wait<1>(); else wg_wait<2>();
        fence_regs(d2[0][0]);
        fence_regs(d2[1][0]);
        fft_e2(d2[0][0], d2[1][0], a3[0]);
        if (it == 2) wg_wait<2>(); else if (it == 3) wg_wait<0>(); else wg_wait<1>();
        fence_regs(d2[0][1]);
        fence_regs(d2[1][1]);
        fft_e2(d2[0][1], d2[1][1], a3[1]);
        wg_fence();
        hmma_n32<0, 1>(d3[0], a3[0][0], db3);
        hmma_n32<0, 1>(d3[1], a3[1][0], db3 + 128);
        hmma_n32<1, 1>(d3[0], a3[0][1], db3 + 32);
        hmma_n32<1, 1>(d3[1], a3[1][1], db3 + 160);
        wg_commit();
        if (it < 3) {
          wg_wait<1>();
          if (it == 2) {
            if (wtid == 64) mbar_arrive(bars + 8 * BAR_DEAD);
            e4(0);
          }
          fence_regs(d1);
          fft_e1<0>(d1, tw, a2[0]);
          s2a();
          wg_commit();
          wg_wait<1>();
        }
        if (it == 3) wg_wait<0>();
        if (it == 3 && wtid == 64) mbar_arrive(bars + 8 * (BAR_DEAD + 1));
        fence_regs(d3[0]);
        fence_regs(d3[1]);
        fft_e3(d3, tw, za + (it & 1) * 512);
        if (it < 3) {
          fft_e1<1>(d1, tw, a2[1]);
          s2b();
        }
        if (it & 1) {
          fence_async_smem();
          nb_sync(NB_WG + wg, 128);
          if (it == 1 && signaller) mbar_arrive_cluster(rbars + 8 * BAR_LFREE);
          s4();
        }
        if (it < 2) s1(it + 2);
        if (w == 0) PROF3(40 + 4 * wg + it);
      }
      if (MODE == 0) {
        mbar_wait(bars + 8 * BAR_FULL2, 0);
        g2_step(0, 0);
        wg_wait<1>();
      } else {
        wg_wait<0>();
      }
      if (signaller) mbar_arrive_cluster(rbars + 8 * (BAR_EMPTY2 + 4));
      e4(1);
      if (MODE == 0) {
        wg_wait<0>();
        if (signaller) mbar_arrive_cluster(rbars + 8 * BAR_EMPTY2);
      }
      PROF(6 + wg);
    }
    }

    if (MODE != 1) {
      int s = MODE == 0, ph = 0;
#pragma unroll 1
      for (int kb = s; kb < STAG; kb++) {
        mbar_wait(bars + 8 * (BAR_FULL2 + s), ph);
        if (kb == 1) PROF(8 + wg);
        if (warp == 4) PROF2(40 + kb);
        g2_step(s, kb);
        wg_wait<0>();
        if (kb < 16 - NS2 && signaller) mbar_arrive_cluster(rbars + 8 * (BAR_EMPTY2 + s));
        if (++s == NS2) { s = 0; ph ^= 1; }
      }
      {
        if (wg == 0) nb_sync(NB_LEAD, 256);
#pragma unroll
        for (int kb = STAG; kb < 16; kb++) {
          mbar_wait(bars + 8 * (BAR_FULL2 + kb % NS2), (kb / NS2) & 1);
          g2_step(kb % NS2, 1);
        }
        if (wg == 1) nb_arrive(NB_LEAD, 256);
      }
      wg_wait<0>();
      fence_regs(acc);
      PROF(10 + wg);
      const int lr = lane & 7, lm = lane >> 3;
      const uint32_t wbase = sb + warp * 2048;
      const uint32_t base = wbase + (lr + 8 * (lm & 1)) * 128;
#pragma unroll
      for (int j = 0; j < 16; j += 2) {
        const uint32_t a = base + (j >> 3) * 16384 + ((((j & 7) + (lm >> 1)) ^ lr) << 4);
        stsm4(a, pack_bf16(acc[4 * j], acc[4 * j + 1]), pack_bf16(acc[4 * j + 2], acc[4 * j + 3]),
              pack_bf16(acc[4 * j + 4], acc[4 * j + 5]), pack_bf16(acc[4 * j + 6], acc[4 * j + 7]));
      }
      __syncwarp();
      {
        const int rr = lane >> 4, ck = lane & 7, hf = (lane >> 3) & 1;
        uint4* og = reinterpret_cast<uint4*>(p.out + (size_t)(2 * ((rb2 & 7) * 128 + warp * 16 + rr) + (rb2 >> 3)) * (2 * DM) + DM + cb2 * 128 + hf * 64 + ck * 8);
        uint4 v[8];
#pragma unroll
        for (int i = 0; i < 8; i++) v[i] = lds128(wbase + hf * 16384 + (2 * i + rr) * 128 + ((ck ^ ((2 * i + rr) & 7)) << 4));
#pragma unroll
        for (int i = 0; i < 8; i++) og[(size_t)i * 4 * (2 * DM / 8)] = v[i];
      }
      PROF(12 + wg);
    }
    cluster_sync_all();
  }
}

typedef CUresult (*EncodeFn)(CUtensorMap*, CUtensorMapDataType, cuuint32_t, void*, const cuuint64_t*, const cuuint64_t*,
                             const cuuint32_t*, const cuuint32_t*, CUtensorMapInterleave, CUtensorMapSwizzle,
                             CUtensorMapL2promotion, CUtensorMapFloatOOBfill);

void make_map(EncodeFn enc, CUtensorMap* tm, const void* base, int rank, const cuuint64_t* dims, const cuuint64_t* strides,
              const cuuint32_t* box, CUtensorMapSwizzle swz) {
  cuuint32_t es[5] = {1, 1, 1, 1, 1};
  enc(tm, CU_TENSOR_MAP_DATA_TYPE_BFLOAT16, rank, const_cast<void*>(base), dims, strides, box, es,
      CU_TENSOR_MAP_INTERLEAVE_NONE, swz, CU_TENSOR_MAP_L2_PROMOTION_L2_256B, CU_TENSOR_MAP_FLOAT_OOB_FILL_NONE);
}

}

extern "C" void kernel_launch(void* const* d_in, const int* in_sizes, int n_in, void* d_out, int out_size) {
  static EncodeFn enc = nullptr;
  static bool coresident = true;
  if (!enc) {
    void* fn = nullptr;
    cudaDriverEntryPointQueryResult qr;
    cudaGetDriverEntryPoint("cuTensorMapEncodeTiled", &fn, cudaEnableDefault, &qr);
    enc = (EncodeFn)fn;
    cudaFuncSetAttribute(fused_kernel<0>, cudaFuncAttributeMaxDynamicSharedMemorySize, SMEM_BYTES);
    cudaFuncSetAttribute(fused_kernel<1>, cudaFuncAttributeMaxDynamicSharedMemorySize, SMEM_BYTES);
    cudaFuncSetAttribute(fused_kernel<2>, cudaFuncAttributeMaxDynamicSharedMemorySize, SMEM_BYTES);
    cudaLaunchConfig_t cfg = {};
    cfg.gridDim = dim3(NCTA);
    cfg.blockDim = dim3(NTHREADS);
    cfg.dynamicSmemBytes = SMEM_BYTES;
    cudaLaunchAttribute at;
    at.id = cudaLaunchAttributeClusterDimension;
    at.val.clusterDim.x = 2;
    at.val.clusterDim.y = 1;
    at.val.clusterDim.z = 1;
    cfg.attrs = &at;
    cfg.numAttrs = 1;
    int nclusters = 0;
    if (cudaOccupancyMaxActiveClusters(&nclusters, fused_kernel<0>, &cfg) == cudaSuccess) coresident = nclusters >= NCTA / 2;
    (void)cudaGetLastError();
  }
  CUtensorMap tmX, tmW, tmWo, tmQ, tmXh, tmWh;
  {
    cuuint64_t dims[3] = {1024, 2, 1024};
    cuuint64_t str[2] = {2048, 4096};
    cuuint32_t box[3] = {64, 1, 128};
    make_map(enc, &tmX, d_in[6], 3, dims, str, box, CU_TENSOR_MAP_SWIZZLE_128B);
  }
  {
    cuuint64_t dims[3] = {1024, 1024, 3};
    cuuint64_t str[2] = {6144, 2048};
    cuuint32_t box[3] = {64, 32, 3};
    make_map(enc, &tmW, d_in[7], 3, dims, str, box, CU_TENSOR_MAP_SWIZZLE_128B);
  }
  {
    cuuint64_t dims[3] = {64, 1024, 16};
    cuuint64_t str[2] = {2048, 128};
    cuuint32_t box[3] = {64, 64, 2};
    make_map(enc, &tmWo, d_in[8], 3, dims, str, box, CU_TENSOR_MAP_SWIZZLE_128B);
  }
  {
    cuuint64_t dims[5] = {1024, 2, 2, 8, 64};
    cuuint64_t str[4] = {2048, 16 * 2048, 2 * 2048, 32 * 2048};
    cuuint32_t box[5] = {16, 2, 2, 8, 4};
    make_map(enc, &tmQ, d_in[0], 5, dims, str, box, CU_TENSOR_MAP_SWIZZLE_NONE);
  }
  {
    cuuint64_t dims[4] = {1024, 256, 2, 4};
    cuuint64_t str[3] = {4096, 2048, 256 * 4096};
    cuuint32_t box[4] = {64, 8, 2, 4};
    make_map(enc, &tmXh, d_in[6], 4, dims, str, box, CU_TENSOR_MAP_SWIZZLE_128B);
  }
  {
    cuuint64_t dims[3] = {64, 1024, 48};
    cuuint64_t str[2] = {6144, 128};
    cuuint32_t box[3] = {64, 64, 4};
    make_map(enc, &tmWh, d_in[7], 3, dims, str, box, CU_TENSOR_MAP_SWIZZLE_128B);
  }
  Params p;
  p.q = (const __nv_bfloat16*)d_in[0];
  p.k = (const __nv_bfloat16*)d_in[1];
  p.v = (const __nv_bfloat16*)d_in[2];
  p.shift_k = (const __nv_bfloat16*)d_in[3];
  p.ssm_k = (const __nv_bfloat16*)d_in[4];
  p.ssm_D = (const __nv_bfloat16*)d_in[5];
  p.x = (const __nv_bfloat16*)d_in[6];
  p.w = (const __nv_bfloat16*)d_in[7];
  p.wo = (const __nv_bfloat16*)d_in[8];
  p.out = (__nv_bfloat16*)d_out;
  if (coresident) {
    fused_kernel<0><<<NCTA, NTHREADS, SMEM_BYTES>>>(p, tmX, tmW, tmWo, tmQ, tmXh, tmWh);
  } else {
    fused_kernel<0><<<4, NTHREADS, SMEM_BYTES>>>(p, tmX, tmW, tmWo, tmQ, tmXh, tmWh);
    fused_kernel<1><<<NCTA, NTHREADS, SMEM_BYTES>>>(p, tmX, tmW, tmWo, tmQ, tmXh, tmWh);
    fused_kernel<2><<<NCTA, NTHREADS, SMEM_BYTES>>>(p, tmX, tmW, tmWo, tmQ, tmXh, tmWh);
  }
}
```
